```python
import torch

def _softmax(x, axis=-1):
    return torch.softmax(x, dim=axis)
def _gelu(x):
    return torch.nn.functional.gelu(x, approximate="tanh")
def _silu(x):
    return torch.nn.functional.silu(x)
def _sigmoid(x):
    return torch.sigmoid(x)
def _layernorm(x, axis=-1, eps=1e-5):
    m = x.mean(dim=axis, keepdim=True)
    v = x.var(dim=axis, keepdim=True, unbiased=False)
    return (x - m) / torch.sqrt(v + eps)
def _scatter_add(tgt, idx, src, axis=0):
    return tgt.clone().index_add_(axis, idx, src)
def _segment_sum(src, seg, n):
    out = torch.zeros((n,) + src.shape[1:], dtype=src.dtype)
    return out.index_add_(0, seg, src)
def _pad(x, pw):
    flat = tuple(v for pair in reversed(pw) for v in pair)
    return torch.nn.functional.pad(x, flat)

kernel_name = 'gated_mix__ssm_conv_h3__sliding_local_dilated__prompt'

def setup_inputs():

    _w = (lambda a: (lambda t: t.to(torch.bfloat16) if t.is_floating_point() else t)(torch.as_tensor(a)))
    def _A_setup():
        B, S, D = 1, 2048, 640
        ks = 4
        return {
            "q": _w((lambda *s: torch.randn(*s, dtype=torch.bfloat16) * 0.05)(B, S, D)),
            "k": _w((lambda *s: torch.randn(*s, dtype=torch.bfloat16) * 0.8)(B, S, D)),
            "v": _w((lambda *s: torch.randn(*s, dtype=torch.bfloat16) * 0.8)(B, S, D)),
            "shift_k": _w((lambda *s: torch.randn(*s, dtype=torch.bfloat16) * 0.8)(D, ks) * 0.5),
            "ssm_k": _w((lambda *s: torch.randn(*s, dtype=torch.bfloat16) * 3.2)(D, S) * (1.0 / S ** 0.5)),
            "ssm_D": _w((lambda *s: torch.randn(*s, dtype=torch.bfloat16) * 0.8)(D)),
        }
    _A_in = _A_setup()

    def _B_setup():
        B, S, D = 1, 2048, 640
        return {
            "x": _w((lambda *s: torch.randn(*s, dtype=torch.bfloat16) * 0.05)(B, S, D)),
            "wqkv": _w((lambda *s: torch.randn(*s, dtype=torch.bfloat16) * 0.8)(D, 3 * D)),
            "wo": _w((lambda *s: torch.randn(*s, dtype=torch.bfloat16) * 0.05)(D, D)),
        }
    _B_in = _B_setup()

    return {
        "A_q": _A_in["q"],
        "A_k": _A_in["k"],
        "A_v": _A_in["v"],
        "A_shift_k": _A_in["shift_k"],
        "A_ssm_k": _A_in["ssm_k"],
        "A_ssm_D": _A_in["ssm_D"],
        "B_x": _B_in["x"],
        "B_wqkv": _B_in["wqkv"],
        "B_wo": _B_in["wo"],
        "gate_w": _w((lambda *s: torch.randn(*s, dtype=torch.bfloat16) * 0.05)(640) * 16.0),
    }

def reference(A_q, A_k, A_v, A_shift_k, A_ssm_k, A_ssm_D, B_x, B_wqkv, B_wo, gate_w):
    def _A_ref(q, k, v, shift_k, ssm_k, ssm_D):
        B, S, D = q.shape
        ks = shift_k.shape[-1]
        k_pad = _pad(k, ((0, 0), (ks - 1, 0), (0, 0)))
        k_shift = torch.zeros_like(k)
        for t in range(ks):
            k_shift = k_shift + k_pad[:, t:t + S, :] * shift_k[:, ks - 1 - t][None, None, :]
        kv = k_shift * v
        L = 2 * S
        kv_pad = _pad(kv, ((0, 0), (0, S), (0, 0)))
        kf_pad = _pad(ssm_k, ((0, 0), (0, S)))
        kv_f = (lambda x, axes=(-2,-1): torch.fft.rfft2(x.float(), dim=axes))(kv_pad[:, None, :, :], axes=(1, 2))
        kf_f = (lambda x, axes=(-2,-1): torch.fft.rfft2(x.float(), dim=axes))(kf_pad[:, None, :], axes=(1, 2))
        kf_f = (lambda x, *d: x.permute(*d))(kf_f, 1, 2, 0)
        y_f = kv_f * kf_f[None, :, :, :]
        y = (lambda x, s, axes=(-2,-1): torch.fft.irfft2(x, s=s, dim=axes).to(torch.bfloat16))(y_f, (1, L), axes=(1, 2))[:, 0, :S, :]
        y = y + kv * ssm_D[None, None, :]
        return q * y

    def _B_ref(x, wqkv, wo):
        B, S, D = x.shape
        H = 32; Dh = D // H
        W, dil = 8, 2
        qkv = (lambda x, *d: x.permute(*d))((x @ wqkv).reshape(B, S, 3, H, Dh), 2, 0, 3, 1, 4)
        q, k, v = qkv[0], qkv[1], qkv[2]
        scale = Dh ** -0.5
        pos = torch.arange(S)
        off = torch.arange(W) * dil
        idx = pos[:, None] - off[None, :]
        mask = idx >= 0
        idx_c = torch.where(mask, idx, 0).reshape(-1)
        kg = k[:, :, idx_c, :].reshape(B, H, S, W, Dh)
        vg = v[:, :, idx_c, :].reshape(B, H, S, W, Dh)
        logits = torch.einsum("bhsd,bhswd->bhsw", q, kg) * scale
        logits = torch.where(mask[None, None, :, :], logits, -1e9)
        attn = _softmax(logits, axis=-1)
        o = torch.einsum("bhsw,bhswd->bhsd", attn, vg)
        return (lambda x, *d: x.permute(*d))(o, 0, 2, 1, 3).reshape(B, S, D) @ wo

    x = A_q
    g = _sigmoid((x * gate_w).sum(-1, keepdims=True))
    a = _A_ref(x, A_k, A_v, A_shift_k, A_ssm_k, A_ssm_D)
    b = _B_ref(x, B_wqkv, B_wo)
    return g * a + (1 - g) * b
```

```cpp
#include <cuda.h>
#include <cuda_bf16.h>
#include <cuda_runtime.h>
#include <stdint.h>

namespace {

constexpr int SEQ = 2048, DIM = 640, NCTA = 128, NTHR = 512;

#define TRIG_KB 9
#define KV_KB 2
#define DEV_EXIT 0
#define ATT_GATE 1
#define G_AFTER 0
#define FENCE_LO 0
#define FENCE_HI 0
#define PW1 2
#define PW2 1
#define ENDBAR 0
#define PAD_KB 0
#define Y_ALIAS 1
#define H_EARLY 1
#define SRC_ROT 0
#define WAIT_NS 0
#define WB_TRIG B_ATTN
#define G_POS 0
#define TAILF 1
#define T_ISSUE 384
#define T_PF 416
#define T_INIT 448
#define ATT_MERGE 0
#define BMAP 1
#define PRE2 1
#define KV_MIX 0
#define O_DEFER 0
#define TOK_G 1
#define RF_GATE 0
#define WO_TRIG B_OSIG
#define WO_GATE 1

constexpr uint32_t STAGE_BYTES = 47104, ST_W = 16384, ST_WT = 40960;
constexpr uint32_t O_BYTES = 20480, WO_BYTES = 12800;
constexpr uint32_t OFF_OA = 0;
constexpr uint32_t OFF_QS = 3 * O_BYTES, OFF_QT = OFF_QS + 16384;
constexpr uint32_t OFF_WC = 81920;
constexpr uint32_t OFF_WA = 94720;
constexpr uint32_t OFF_GATE = 145920;
constexpr uint32_t OFF_KVX = 147968;
constexpr uint32_t OFF_D = OFF_GATE + 512;
constexpr uint32_t OFF_CH3 = 163840;
constexpr uint32_t CH_BYTES = 12288, U_BYTES = 4096;
constexpr uint32_t OFF_FT = 225280, OFF_GT = 229376;
constexpr uint32_t OFF_CH0 = 188416;
constexpr uint32_t OFF_KVS = OFF_CH0, KVS_V = 4480, KVS_BYTES = 8576;
constexpr uint32_t OFF_YT = 163840;
constexpr uint32_t OFF_BAR = 231936;
constexpr uint32_t SMEM_BYTES = OFF_BAR + 512;

enum : uint32_t {
  B_FULL1 = 0, B_EMPTY1 = 4, B_S3 = 7, B_FULL2 = 52, B_EMPTY2 = 13, B_U = 8, B_GATE = 12, B_HA = 19, B_HB = 20,
  B_ATTN = 21, B_C34 = 22, B_CONV = 23, B_YFULL = 24, B_EPOCH = 25, B_PREP = 26, B_P1 = 27, B_LAST = 28,
  B_E3 = 29, B_OSIG = 30, B_WOP = 31, B_USIG = 32, B_WST = 33, B_KV = 34, B_KVD = 39, B_HC = 61, B_QF = 62, B_YST = 40,
  B_TOK = 45, B_YSIG = 50
};
constexpr uint32_t OFF_EPOCH = OFF_BAR + 8 * 51;
__device__ __forceinline__ uint32_t off_o(int j) { return j < 4 ? OFF_OA + j * O_BYTES : j < 6 ? OFF_CH0 + (j - 4) * O_BYTES : OFF_OA + (j - 6) * O_BYTES; }
__device__ __forceinline__ uint32_t off_w(int j) { return j < 4 ? OFF_WA + j * WO_BYTES : j == 4 ? OFF_KVX : j == 5 ? OFF_WC : OFF_WA + (j - 6) * WO_BYTES; }
__device__ __forceinline__ int step_src(int hg, int j) { return SRC_ROT ? (hg + j) & 7 : j == 0 ? hg : j <= hg ? j - 1 : j; }
__device__ __forceinline__ bool tail_first(int hg) { return TAILF && (hg & 3) == 3; }
__device__ __forceinline__ uint32_t off_ch(int c) { return (c < 3 ? OFF_CH0 : OFF_CH3 - 3 * CH_BYTES) + c * CH_BYTES; }

#define U_PITCH 264
__device__ __align__(1024) uint4 g_U[DIM * U_PITCH];
__device__ uint4 g_O[NCTA * 1280];
#define g_Y g_U
constexpr int Y_PITCH = U_PITCH;
__device__ uint4 g_WO[64 * 800];
__device__ uint4 g_halo[NCTA * 2 * 7 * 32];
__device__ float g_gate[SEQ + PAD_KB * 256];
__device__ unsigned g_cnt[32 * (1 + 2 * 16 + 8 + NCTA)];
constexpr int C_LAUNCH = 0, C_PREP = 32, C_Y = 32 * 17, C_W = 32 * 33, C_O = 32 * 41;

#define TSM(cond, slot) do { } while (0)
#define TSIF(cond, slot) do { if (__LINE__ >= FENCE_LO && __LINE__ < FENCE_HI) sched_fence(); } while (0)
__device__ __forceinline__ void sched_fence() {
  asm volatile("{\n.reg .pred p;\n.reg .u32 c;\nmov.u32 c, %%clock;\nsetp.eq.u32 p, c, 0;\n@p st.shared.u32 [%0], c;\n}"
               ::"r"(1024 + OFF_EPOCH + 4) : "memory");
}
#define TS(slot) TSIF(true, slot)

struct Params {
  const __nv_bfloat16 *q, *k, *v, *shift_k, *ssm_k, *ssm_D, *wqkv, *wo, *gate_w;
  __nv_bfloat16* out;
  uint32_t zero;
};

#define POLL_NS 0
constexpr int SPIN_LIMIT = 1 << 17;

__device__ __forceinline__ void mbar_init(uint32_t bar, uint32_t count) {
  asm volatile("mbarrier.init.shared::cta.b64 [%0], %1;" ::"r"(bar), "r"(count) : "memory");
}
__device__ __forceinline__ void mbar_expect_tx(uint32_t bar, uint32_t bytes) {
  asm volatile("mbarrier.arrive.expect_tx.shared::cta.b64 _, [%0], %1;" ::"r"(bar), "r"(bytes) : "memory");
}
__device__ __forceinline__ void mbar_arrive(uint32_t bar) {
  asm volatile("mbarrier.arrive.shared::cta.b64 _, [%0];" ::"r"(bar) : "memory");
}
__device__ __forceinline__ void mbar_wait(uint32_t bar, uint32_t parity) {
  uint32_t ok;
  int spins = 0;
  do {
    if (WAIT_NS)
      asm volatile("{\n.reg .pred p;\nmbarrier.try_wait.parity.shared::cta.b64 p, [%1], %2, %3;\nselp.b32 %0, 1, 0, p;\n}"
                   : "=r"(ok) : "r"(bar), "r"(parity), "r"(WAIT_NS) : "memory");
    else
      asm volatile("{\n.reg .pred p;\nmbarrier.try_wait.parity.shared::cta.b64 p, [%1], %2;\nselp.b32 %0, 1, 0, p;\n}"
                   : "=r"(ok) : "r"(bar), "r"(parity) : "memory");
    if (++spins > SPIN_LIMIT) break;
  } while (!ok);
}
__device__ __forceinline__ void flag_poll(const unsigned* p, unsigned target) {
  unsigned v;
  int spins = 0;
  do {
    if (POLL_NS && spins) __nanosleep(POLL_NS);
    asm volatile("ld.relaxed.gpu.global.u32 %0, [%1];" : "=r"(v) : "l"(p) : "memory");
    if (++spins > SPIN_LIMIT) break;
  } while ((int)(v - target) < 0);
}
__device__ __forceinline__ void flag_wait(const unsigned* p, unsigned target) {
  flag_poll(p, target);
  asm volatile("fence.acquire.gpu;\nfence.proxy.async.global;" ::: "memory");
}
__device__ __forceinline__ void flag_signal(unsigned* p, int n, int lane) {
  if (lane == 0) asm volatile("fence.release.gpu;" ::: "memory");
  __syncwarp();
  if (lane < n) asm volatile("red.relaxed.gpu.global.add.u32 [%0], 1;" ::"l"(p + 32 * lane) : "memory");
}
__device__ __forceinline__ void fence_async_smem() { asm volatile("fence.proxy.async.shared::cta;" ::: "memory"); }
__device__ __forceinline__ void wg_sync(int id) { asm volatile("bar.sync %0, 128;" ::"r"(id) : "memory"); }

__device__ __forceinline__ void tma_2d(uint32_t dst, const CUtensorMap* tm, int c0, int c1, uint32_t bar) {
  asm volatile("cp.async.bulk.tensor.2d.shared::cluster.global.mbarrier::complete_tx::bytes [%0], [%1, {%3, %4}], [%2];"
               ::"r"(dst), "l"(tm), "r"(bar), "r"(c0), "r"(c1) : "memory");
}
__device__ __forceinline__ void tma_3d(uint32_t dst, const CUtensorMap* tm, int c0, int c1, int c2, uint32_t bar) {
  asm volatile("cp.async.bulk.tensor.3d.shared::cluster.global.mbarrier::complete_tx::bytes [%0], [%1, {%3, %4, %5}], [%2];"
               ::"r"(dst), "l"(tm), "r"(bar), "r"(c0), "r"(c1), "r"(c2) : "memory");
}
__device__ __forceinline__ void bulk_load(uint32_t dst, const void* src, uint32_t bytes, uint32_t bar) {
  asm volatile("cp.async.bulk.shared::cluster.global.mbarrier::complete_tx::bytes [%0], [%1], %2, [%3];"
               ::"r"(dst), "l"(src), "r"(bytes), "r"(bar) : "memory");
}
__device__ __forceinline__ void tm_prefetch(const CUtensorMap* tm) {
  asm volatile("prefetch.tensormap [%0];" ::"l"(tm) : "memory");
}

__device__ __forceinline__ void wg_fence() { asm volatile("wgmma.fence.sync.aligned;" ::: "memory"); }
__device__ __forceinline__ void wg_commit() { asm volatile("wgmma.commit_group.sync.aligned;" ::: "memory"); }
template <int N> __device__ __forceinline__ void wg_wait() { asm volatile("wgmma.wait_group.sync.aligned %0;" ::"n"(N) : "memory"); }
__device__ __forceinline__ uint32_t desc_lo(uint32_t addr, uint32_t lbo) { return ((addr & 0x3FFFF) >> 4) | ((lbo >> 4) << 16); }
constexpr uint32_t desc_hi(uint32_t sbo, uint32_t swz) { return (sbo >> 4) | (swz << 30); }
constexpr uint32_t HI_SW128 = desc_hi(1024, 1), HI_SW64 = desc_hi(512, 2), HI_SW32 = desc_hi(256, 3), HI_NONE = desc_hi(128, 0);
template <int N> __device__ __forceinline__ void pin(float* d) {
#pragma unroll
  for (int i = 0; i < N; i++) asm volatile("" : "+f"(d[i])::"memory");
}

__device__ __forceinline__ uint32_t lds32(uint32_t a) {
  uint32_t v;
  asm volatile("ld.volatile.shared.u32 %0, [%1];" : "=r"(v) : "r"(a) : "memory");
  return v;
}
__device__ __forceinline__ uint4 ldg128(const void* a) {
  uint4 v;
  asm volatile("ld.global.nc.v4.u32 {%0, %1, %2, %3}, [%4];" : "=r"(v.x), "=r"(v.y), "=r"(v.z), "=r"(v.w) : "l"(a) : "memory");
  return v;
}
__device__ __forceinline__ uint2 ldg64(const void* a) {
  uint2 v;
  asm volatile("ld.global.nc.v2.u32 {%0, %1}, [%2];" : "=r"(v.x), "=r"(v.y) : "l"(a) : "memory");
  return v;
}
__device__ __forceinline__ void ldsm4(uint32_t* r, uint32_t a) {
  asm volatile("ldmatrix.sync.aligned.m8n8.x4.shared.b16 {%0, %1, %2, %3}, [%4];"
               : "=r"(r[0]), "=r"(r[1]), "=r"(r[2]), "=r"(r[3]) : "r"(a) : "memory");
}
__device__ __forceinline__ void ldsm4t(uint32_t* r, uint32_t a) {
  asm volatile("ldmatrix.sync.aligned.m8n8.x4.trans.shared.b16 {%0, %1, %2, %3}, [%4];"
               : "=r"(r[0]), "=r"(r[1]), "=r"(r[2]), "=r"(r[3]) : "r"(a) : "memory");
}
__device__ __forceinline__ uint4 lds128(uint32_t a) {
  uint4 v;
  asm volatile("ld.shared.v4.u32 {%0, %1, %2, %3}, [%4];" : "=r"(v.x), "=r"(v.y), "=r"(v.z), "=r"(v.w) : "r"(a) : "memory");
  return v;
}
__device__ __forceinline__ void sts128(uint32_t a, uint32_t x, uint32_t y, uint32_t z, uint32_t w) {
  asm volatile("st.shared.v4.u32 [%0], {%1, %2, %3, %4};" ::"r"(a), "r"(x), "r"(y), "r"(z), "r"(w) : "memory");
}
__device__ __forceinline__ void stsm4(uint32_t a, const uint32_t* r) {
  asm volatile("stmatrix.sync.aligned.m8n8.x4.shared.b16 [%0], {%1, %2, %3, %4};" ::"r"(a), "r"(r[0]), "r"(r[1]), "r"(r[2]), "r"(r[3]) : "memory");
}
__device__ __forceinline__ void stsm4t(uint32_t a, const uint32_t* r) {
  asm volatile("stmatrix.sync.aligned.m8n8.x4.trans.shared.b16 [%0], {%1, %2, %3, %4};" ::"r"(a), "r"(r[0]), "r"(r[1]), "r"(r[2]), "r"(r[3]) : "memory");
}
__device__ __forceinline__ uint32_t pack2(float lo, float hi) {
  uint32_t r;
  asm("cvt.rn.bf16x2.f32 %0, %1, %2;" : "=r"(r) : "f"(hi), "f"(lo));
  return r;
}
__device__ __forceinline__ uint32_t movm(uint32_t a) {
  uint32_t d;
  asm volatile("movmatrix.sync.aligned.m8n8.trans.b16 %0, %1;" : "=r"(d) : "r"(a));
  return d;
}
__device__ __forceinline__ uint32_t bmul(uint32_t a, uint32_t b) {
  uint32_t d;
  asm("mul.rn.bf16x2 %0, %1, %2;" : "=r"(d) : "r"(a), "r"(b));
  return d;
}
__device__ __forceinline__ uint32_t badd(uint32_t a, uint32_t b) {
  uint32_t d;
  asm("add.rn.bf16x2 %0, %1, %2;" : "=r"(d) : "r"(a), "r"(b));
  return d;
}
__device__ __forceinline__ float bf_lo(uint32_t x) { return __uint_as_float(x << 16); }
__device__ __forceinline__ float bf_hi(uint32_t x) { return __uint_as_float(x & 0xFFFF0000u); }
__device__ __forceinline__ float ex2(float x) {
  float y;
  asm("ex2.approx.ftz.f32 %0, %1;" : "=f"(y) : "f"(x));
  return y;
}
__device__ __forceinline__ float rcp(float x) {
  float y;
  asm("rcp.approx.ftz.f32 %0, %1;" : "=f"(y) : "f"(x));
  return y;
}
__device__ __forceinline__ void mma16816(float* d, uint32_t a0, uint32_t a1, uint32_t a2, uint32_t a3, uint32_t b0, uint32_t b1) {
  asm volatile("mma.sync.aligned.m16n8k16.row.col.f32.bf16.bf16.f32 {%0, %1, %2, %3}, {%4, %5, %6, %7}, {%8, %9}, {%0, %1, %2, %3};"
               : "+f"(d[0]), "+f"(d[1]), "+f"(d[2]), "+f"(d[3])
               : "r"(a0), "r"(a1), "r"(a2), "r"(a3), "r"(b0), "r"(b1));
}
__device__ __forceinline__ void mma1688(float* d, uint32_t a0, uint32_t a1, uint32_t b0) {
  asm volatile("mma.sync.aligned.m16n8k8.row.col.f32.bf16.bf16.f32 {%0, %1, %2, %3}, {%4, %5}, {%6}, {%0, %1, %2, %3};"
               : "+f"(d[0]), "+f"(d[1]), "+f"(d[2]), "+f"(d[3])
               : "r"(a0), "r"(a1), "r"(b0));
}

template <int N> struct WgRS;
template <int N> struct WgSST;
template <> struct WgRS<32> {
  template <uint32_t HB>
  static __device__ __forceinline__ void mma(float* d, const uint32_t* a, uint32_t db) {
    asm volatile("{\n.reg .pred p;\n.reg .b64 db;\nsetp.ne.b32 p, %22, 0;\n"
      "mov.b64 db, {%20, %21};\n"
      "wgmma.mma_async.sync.aligned.m64n32k16.f32.bf16.bf16 {"
      "%0, %1, %2, %3, %4, %5, %6, %7, %8, %9, %10, %11, %12, %13, %14, %15"
      "}, {%16, %17, %18, %19}, db, p, 1, 1, 1;\n}\n"
      : "+f"(d[0]), "+f"(d[1]), "+f"(d[2]), "+f"(d[3]), "+f"(d[4]), "+f"(d[5]), "+f"(d[6]), "+f"(d[7]),
        "+f"(d[8]), "+f"(d[9]), "+f"(d[10]), "+f"(d[11]), "+f"(d[12]), "+f"(d[13]), "+f"(d[14]), "+f"(d[15])
      : "r"(a[0]), "r"(a[1]), "r"(a[2]), "r"(a[3]), "r"(db), "n"(HB), "n"(1));
  }
  template <uint32_t HB>
  static __device__ __forceinline__ void set(float* d, const uint32_t* a, uint32_t db) {
    asm volatile("{\n.reg .pred p;\n.reg .b64 db;\nsetp.ne.b32 p, %22, 0;\n"
      "mov.b64 db, {%20, %21};\n"
      "wgmma.mma_async.sync.aligned.m64n32k16.f32.bf16.bf16 {"
      "%0, %1, %2, %3, %4, %5, %6, %7, %8, %9, %10, %11, %12, %13, %14, %15"
      "}, {%16, %17, %18, %19}, db, p, 1, 1, 1;\n}\n"
      : "=f"(d[0]), "=f"(d[1]), "=f"(d[2]), "=f"(d[3]), "=f"(d[4]), "=f"(d[5]), "=f"(d[6]), "=f"(d[7]),
        "=f"(d[8]), "=f"(d[9]), "=f"(d[10]), "=f"(d[11]), "=f"(d[12]), "=f"(d[13]), "=f"(d[14]), "=f"(d[15])
      : "r"(a[0]), "r"(a[1]), "r"(a[2]), "r"(a[3]), "r"(db), "n"(HB), "n"(0));
  }
};
template <> struct WgRS<64> {
  template <uint32_t HB>
  static __device__ __forceinline__ void mma(float* d, const uint32_t* a, uint32_t db) {
    asm volatile("{\n.reg .pred p;\n.reg .b64 db;\nsetp.ne.b32 p, %38, 0;\n"
      "mov.b64 db, {%36, %37};\n"
      "wgmma.mma_async.sync.aligned.m64n64k16.f32.bf16.bf16 {"
      "%0, %1, %2, %3, %4, %5, %6, %7, %8, %9, %10, %11, %12, %13, %14, %15, "
      "%16, %17, %18, %19, %20, %21, %22, %23, %24, %25, %26, %27, %28, %29, %30, %31"
      "}, {%32, %33, %34, %35}, db, p, 1, 1, 1;\n}\n"
      : "+f"(d[0]), "+f"(d[1]), "+f"(d[2]), "+f"(d[3]), "+f"(d[4]), "+f"(d[5]), "+f"(d[6]), "+f"(d[7]),
        "+f"(d[8]), "+f"(d[9]), "+f"(d[10]), "+f"(d[11]), "+f"(d[12]), "+f"(d[13]), "+f"(d[14]), "+f"(d[15]),
        "+f"(d[16]), "+f"(d[17]), "+f"(d[18]), "+f"(d[19]), "+f"(d[20]), "+f"(d[21]), "+f"(d[22]), "+f"(d[23]),
        "+f"(d[24]), "+f"(d[25]), "+f"(d[26]), "+f"(d[27]), "+f"(d[28]), "+f"(d[29]), "+f"(d[30]), "+f"(d[31])
      : "r"(a[0]), "r"(a[1]), "r"(a[2]), "r"(a[3]), "r"(db), "n"(HB), "n"(1));
  }
  template <uint32_t HB>
  static __device__ __forceinline__ void set(float* d, const uint32_t* a, uint32_t db) {
    asm volatile("{\n.reg .pred p;\n.reg .b64 db;\nsetp.ne.b32 p, %38, 0;\n"
      "mov.b64 db, {%36, %37};\n"
      "wgmma.mma_async.sync.aligned.m64n64k16.f32.bf16.bf16 {"
      "%0, %1, %2, %3, %4, %5, %6, %7, %8, %9, %10, %11, %12, %13, %14, %15, "
      "%16, %17, %18, %19, %20, %21, %22, %23, %24, %25, %26, %27, %28, %29, %30, %31"
      "}, {%32, %33, %34, %35}, db, p, 1, 1, 1;\n}\n"
      : "=f"(d[0]), "=f"(d[1]), "=f"(d[2]), "=f"(d[3]), "=f"(d[4]), "=f"(d[5]), "=f"(d[6]), "=f"(d[7]),
        "=f"(d[8]), "=f"(d[9]), "=f"(d[10]), "=f"(d[11]), "=f"(d[12]), "=f"(d[13]), "=f"(d[14]), "=f"(d[15]),
        "=f"(d[16]), "=f"(d[17]), "=f"(d[18]), "=f"(d[19]), "=f"(d[20]), "=f"(d[21]), "=f"(d[22]), "=f"(d[23]),
        "=f"(d[24]), "=f"(d[25]), "=f"(d[26]), "=f"(d[27]), "=f"(d[28]), "=f"(d[29]), "=f"(d[30]), "=f"(d[31])
      : "r"(a[0]), "r"(a[1]), "r"(a[2]), "r"(a[3]), "r"(db), "n"(HB), "n"(0));
  }
};
template <> struct WgSST<48> {
  template <uint32_t HA, uint32_t HB>
  static __device__ __forceinline__ void mma(float* d, uint32_t da, uint32_t db, int sc) {
    asm volatile("{\n.reg .pred p;\n.reg .b64 da, db;\nsetp.ne.b32 p, %28, 0;\n"
      "mov.b64 da, {%24, %25};\nmov.b64 db, {%26, %27};\n"
      "wgmma.mma_async.sync.aligned.m64n48k16.f32.bf16.bf16 {"
      "%0, %1, %2, %3, %4, %5, %6, %7, %8, %9, %10, %11, %12, %13, %14, %15, "
      "%16, %17, %18, %19, %20, %21, %22, %23"
      "}, da, db, p, 1, 1, 0, 1;\n}\n"
      : "+f"(d[0]), "+f"(d[1]), "+f"(d[2]), "+f"(d[3]), "+f"(d[4]), "+f"(d[5]), "+f"(d[6]), "+f"(d[7]),
        "+f"(d[8]), "+f"(d[9]), "+f"(d[10]), "+f"(d[11]), "+f"(d[12]), "+f"(d[13]), "+f"(d[14]), "+f"(d[15]),
        "+f"(d[16]), "+f"(d[17]), "+f"(d[18]), "+f"(d[19]), "+f"(d[20]), "+f"(d[21]), "+f"(d[22]), "+f"(d[23])
      : "r"(da), "n"(HA), "r"(db), "n"(HB), "r"(sc));
  }
};
template <> struct WgSST<80> {
  template <uint32_t HA, uint32_t HB>
  static __device__ __forceinline__ void mma(float* d, uint32_t da, uint32_t db, int sc) {
    asm volatile("{\n.reg .pred p;\n.reg .b64 da, db;\nsetp.ne.b32 p, %44, 0;\n"
      "mov.b64 da, {%40, %41};\nmov.b64 db, {%42, %43};\n"
      "wgmma.mma_async.sync.aligned.m64n80k16.f32.bf16.bf16 {"
      "%0, %1, %2, %3, %4, %5, %6, %7, %8, %9, %10, %11, %12, %13, %14, %15, "
      "%16, %17, %18, %19, %20, %21, %22, %23, %24, %25, %26, %27, %28, %29, %30, %31, "
      "%32, %33, %34, %35, %36, %37, %38, %39"
      "}, da, db, p, 1, 1, 0, 1;\n}\n"
      : "+f"(d[0]), "+f"(d[1]), "+f"(d[2]), "+f"(d[3]), "+f"(d[4]), "+f"(d[5]), "+f"(d[6]), "+f"(d[7]),
        "+f"(d[8]), "+f"(d[9]), "+f"(d[10]), "+f"(d[11]), "+f"(d[12]), "+f"(d[13]), "+f"(d[14]), "+f"(d[15]),
        "+f"(d[16]), "+f"(d[17]), "+f"(d[18]), "+f"(d[19]), "+f"(d[20]), "+f"(d[21]), "+f"(d[22]), "+f"(d[23]),
        "+f"(d[24]), "+f"(d[25]), "+f"(d[26]), "+f"(d[27]), "+f"(d[28]), "+f"(d[29]), "+f"(d[30]), "+f"(d[31]),
        "+f"(d[32]), "+f"(d[33]), "+f"(d[34]), "+f"(d[35]), "+f"(d[36]), "+f"(d[37]), "+f"(d[38]), "+f"(d[39])
      : "r"(da), "n"(HA), "r"(db), "n"(HB), "r"(sc));
  }
};
template <> struct WgSST<192> {
  template <uint32_t HA, uint32_t HB>
  static __device__ __forceinline__ void mma(float* d, uint32_t da, uint32_t db, int sc) {
    asm volatile("{\n.reg .pred p;\n.reg .b64 da, db;\nsetp.ne.b32 p, %100, 0;\n"
      "mov.b64 da, {%96, %97};\nmov.b64 db, {%98, %99};\n"
      "wgmma.mma_async.sync.aligned.m64n192k16.f32.bf16.bf16 {"
      "%0, %1, %2, %3, %4, %5, %6, %7, %8, %9, %10, %11, %12, %13, %14, %15, "
      "%16, %17, %18, %19, %20, %21, %22, %23, %24, %25, %26, %27, %28, %29, %30, %31, "
      "%32, %33, %34, %35, %36, %37, %38, %39, %40, %41, %42, %43, %44, %45, %46, %47, "
      "%48, %49, %50, %51, %52, %53, %54, %55, %56, %57, %58, %59, %60, %61, %62, %63, "
      "%64, %65, %66, %67, %68, %69, %70, %71, %72, %73, %74, %75, %76, %77, %78, %79, "
      "%80, %81, %82, %83, %84, %85, %86, %87, %88, %89, %90, %91, %92, %93, %94, %95"
      "}, da, db, p, 1, 1, 0, 1;\n}\n"
      : "+f"(d[0]), "+f"(d[1]), "+f"(d[2]), "+f"(d[3]), "+f"(d[4]), "+f"(d[5]), "+f"(d[6]), "+f"(d[7]),
        "+f"(d[8]), "+f"(d[9]), "+f"(d[10]), "+f"(d[11]), "+f"(d[12]), "+f"(d[13]), "+f"(d[14]), "+f"(d[15]),
        "+f"(d[16]), "+f"(d[17]), "+f"(d[18]), "+f"(d[19]), "+f"(d[20]), "+f"(d[21]), "+f"(d[22]), "+f"(d[23]),
        "+f"(d[24]), "+f"(d[25]), "+f"(d[26]), "+f"(d[27]), "+f"(d[28]), "+f"(d[29]), "+f"(d[30]), "+f"(d[31]),
        "+f"(d[32]), "+f"(d[33]), "+f"(d[34]), "+f"(d[35]), "+f"(d[36]), "+f"(d[37]), "+f"(d[38]), "+f"(d[39]),
        "+f"(d[40]), "+f"(d[41]), "+f"(d[42]), "+f"(d[43]), "+f"(d[44]), "+f"(d[45]), "+f"(d[46]), "+f"(d[47]),
        "+f"(d[48]), "+f"(d[49]), "+f"(d[50]), "+f"(d[51]), "+f"(d[52]), "+f"(d[53]), "+f"(d[54]), "+f"(d[55]),
        "+f"(d[56]), "+f"(d[57]), "+f"(d[58]), "+f"(d[59]), "+f"(d[60]), "+f"(d[61]), "+f"(d[62]), "+f"(d[63]),
        "+f"(d[64]), "+f"(d[65]), "+f"(d[66]), "+f"(d[67]), "+f"(d[68]), "+f"(d[69]), "+f"(d[70]), "+f"(d[71]),
        "+f"(d[72]), "+f"(d[73]), "+f"(d[74]), "+f"(d[75]), "+f"(d[76]), "+f"(d[77]), "+f"(d[78]), "+f"(d[79]),
        "+f"(d[80]), "+f"(d[81]), "+f"(d[82]), "+f"(d[83]), "+f"(d[84]), "+f"(d[85]), "+f"(d[86]), "+f"(d[87]),
        "+f"(d[88]), "+f"(d[89]), "+f"(d[90]), "+f"(d[91]), "+f"(d[92]), "+f"(d[93]), "+f"(d[94]), "+f"(d[95])
      : "r"(da), "n"(HA), "r"(db), "n"(HB), "r"(sc));
  }
};

struct FftConst {
  uint32_t f[2][4], fi[4][4];
  float ta[4], tb[4];
};
__device__ __forceinline__ void cis(int m, float scale, float& c, float& s) {
  const float a = (float)m * (-6.283185307179586f * scale);
  c = __cosf(a);
  s = __sinf(a);
}
__device__ __forceinline__ void fft_tables(uint32_t (&v)[12], int tw) {
  const int row = tw >> 2, ch = tw & 3;
#pragma unroll
  for (int i = 0; i < 4; i++) {
    float c[2], s[2], x[2];
#pragma unroll
    for (int e = 0; e < 2; e++) {
      cis((((32 * (8 * ch + 2 * i + e) + 15) * (4 * row - 63) + 2048) & 4095) - 2048, 1.f / 4096, c[e], s[e]);
      float gc, gs;
      cis((((row & 15) * (8 * (ch & 1) + 2 * i + e) + 8) & 15) - 8, 1.f / 16, gc, gs);
      x[e] = (row >> 4) == (ch >> 1) ? gc : (ch >> 1) ? gs : -gs;
    }
    v[i] = pack2(c[0] * 0.125f, c[1] * 0.125f);
    v[4 + i] = pack2(s[0] * 0.125f, s[1] * 0.125f);
    v[8 + i] = pack2(x[0], x[1]);
  }
#pragma unroll
  for (int i = 0; i < 12; i++) asm volatile("" : "+r"(v[i]));
}
__device__ __forceinline__ void fft_tables_store(const uint32_t (&v)[12], uint32_t sb, int tw) {
  const int row = tw >> 2;
  const uint32_t x = ((tw ^ (row >> 1)) & 3) << 4, a = sb + OFF_FT + (16 * (row >> 3) + (row & 7)) * 64 + x;
  sts128(a, v[0], v[1], v[2], v[3]);
  sts128(a + 512, v[4], v[5], v[6], v[7]);
  sts128(sb + OFF_GT + row * 64 + x, v[8], v[9], v[10], v[11]);
}
__device__ __forceinline__ void fft_twiddles(FftConst& k, int w, int lane) {
#pragma unroll
  for (int i = 0; i < 4; i++) {
    float c, s;
    cis((2 * (8 * (i >> 1) + 2 * (lane & 3) + (i & 1)) - 15) * (4 * (8 * w + (lane >> 2)) - 63), 1.f / 4096, c, s);
    k.ta[i] = __fdividef(-s, 1.f + c);
    k.tb[i] = s;
  }
  pin<4>(k.ta);
  pin<4>(k.tb);
}
__device__ __forceinline__ void fft_matrices(FftConst& k, uint32_t sb, int w, int lane) {
  const uint32_t x = (lane >> 1) & 3;
#pragma unroll
  for (int i = 0; i < 2; i++) {
    ldsm4(k.f[i], sb + OFF_FT + (16 * w + (lane & 15)) * 64 + (((2 * i + (lane >> 4)) ^ x) << 4));
    ldsm4t(k.fi[i], sb + OFF_FT + (32 * i + lane) * 64 + ((w ^ x) << 4));
#pragma unroll
    for (int j = 0; j < 4; j++) {
      k.fi[2 + i][j] = (j & 1) ? k.fi[i][j - 1] ^ 0x80008000u : k.fi[i][j + 1];
      asm volatile("" : "+r"(k.fi[2 + i][j]));
    }
  }
}
template <bool INV> __device__ __forceinline__ void rot(float& x, float& y, float a, float b) {
  x = fmaf(INV ? -a : a, y, x);
  y = fmaf(INV ? -b : b, x, y);
  x = fmaf(INV ? -a : a, y, x);
}
__device__ __forceinline__ void twiddle_fwd(uint32_t (&a)[4][4], float* d, const FftConst& k) {
#pragma unroll
  for (int q = 0; q < 4; q++)
#pragma unroll
    for (int j = 0; j < 2; j++) {
      float* x = d + 8 * q + 4 * j;
      rot<false>(x[0], x[2], k.ta[2 * j], k.tb[2 * j]);
      rot<false>(x[1], x[3], k.ta[2 * j + 1], k.tb[2 * j + 1]);
      a[q & 2][2 * j + (q & 1)] = pack2(x[0], x[1]);
      a[(q & 2) + 1][2 * j + (q & 1)] = pack2(x[2], x[3]);
    }
}
__device__ __forceinline__ void g_step(float* d, const uint32_t (&a)[4][4], uint32_t dre, uint32_t dim) {
  WgRS<32>::set<HI_SW64>(d, a[0], dre);
  WgRS<32>::set<HI_SW64>(d + 16, a[2], dre);
  WgRS<32>::mma<HI_SW64>(d, a[1], dim);
  WgRS<32>::mma<HI_SW64>(d + 16, a[3], dim);
  wg_commit();
}

__device__ __forceinline__ void conv_channel(const FftConst& k, uint32_t sb, int c, int wg, int w, int lane) {
  const uint32_t cb = sb + off_ch(c), bars = sb + OFF_BAR;
  const uint32_t du = desc_lo(cb, 1024), dg = desc_lo(sb + OFF_GT, 16), dz = desc_lo(cb + U_BYTES, 16);
  float U[32], H[32];
  uint32_t a[4][4], e[4][4];
  const float dv = __uint_as_float(lds32(sb + OFF_D + 4 * c));
  wg_fence();
  WgRS<64>::set<HI_SW32>(H, k.f[0], du + 256);
  WgRS<64>::mma<HI_SW32>(H, k.f[1], du + 256 + 32);
  wg_commit();
  wg_wait<0>();
  pin<32>(H);
  twiddle_fwd(a, H, k);
  if (ATT_GATE && H_EARLY) mbar_wait(bars + 8 * B_ATTN, 0);
  mbar_wait(bars + 8 * (B_U + (c < 3 ? c : 3)), 0);
  TSM(w == 0 && c < 3, 7 + wg);
  if (TOK_G < 8 && c > 0) mbar_wait(bars + 8 * (B_TOK + c - 1), 0);
  wg_fence();
  WgRS<64>::set<HI_SW32>(U, k.f[0], du);
  WgRS<64>::mma<HI_SW32>(U, k.f[1], du + 32);
  wg_commit();
  g_step(H, a, dg, dg + 64);
  wg_wait<1>();
  pin<32>(U);
  if (TOK_G == 1 && lane == 0) mbar_arrive(bars + 8 * (B_TOK + c));
  twiddle_fwd(e, U, k);
  wg_fence();
  g_step(U, e, dg, dg + 64);
  if (TOK_G == 2 && lane == 0) mbar_arrive(bars + 8 * (B_TOK + c));
  wg_wait<0>();
  pin<32>(U);
  pin<32>(H);
#pragma unroll
  for (int j = 0; j < 2; j++) {
    float pr[4][2], pi[4][2];
#pragma unroll
    for (int x = 0; x < 2; x++) {
      H[4 * j + x] += dv;
#pragma unroll
      for (int m = 0; m < 4; m++) {
#pragma unroll
        for (int q = 0; q <= m; q++) {
          const int ih = 16 * (q >> 1) + 2 * (q & 1) + 4 * j + x, iu = 16 * ((m - q) >> 1) + 2 * ((m - q) & 1) + 4 * j + x;
          pr[m][x] = q ? fmaf(H[ih], U[iu], pr[m][x]) : H[ih] * U[iu];
          pi[m][x] = q ? fmaf(H[ih], U[iu + 8], pi[m][x]) : H[ih] * U[iu + 8];
          pr[m][x] = fmaf(-H[ih + 8], U[iu + 8], pr[m][x]);
          pi[m][x] = fmaf(H[ih + 8], U[iu], pi[m][x]);
        }
      }
    }
#pragma unroll
    for (int m = 0; m < 4; m++) {
      a[m & 2][2 * j + (m & 1)] = pack2(pr[m][0], pr[m][1]);
      a[(m & 2) + 1][2 * j + (m & 1)] = pack2(pi[m][0], pi[m][1]);
    }
  }
  wg_fence();
  g_step(U, a, dg + 64, dg);
  if (TOK_G == 3 && lane == 0) mbar_arrive(bars + 8 * (B_TOK + c));
  const uint32_t za = cb + U_BYTES + (8 * w + (lane & 7)) * 128 + (((lane >> 3) ^ (lane & 7)) << 4);
  const uint32_t ya = cb + (lane >> 4) * 1024 + (8 * w + (lane & 7)) * 32 + ((((lane >> 3) ^ (lane >> 2)) & 1) << 4);
  wg_sync(1 + wg);
  wg_wait<0>();
  pin<32>(U);
  TSIF(w == 0, 80 + c);
#pragma unroll
  for (int p = 0; p < 2; p++) {
#pragma unroll
    for (int i = 0; i < 4; i++) {
      const int j = i & 1;
      float* x = U + 16 * p + 4 * j + (i & 2);
      rot<true>(x[8], x[0], k.ta[2 * j], k.tb[2 * j]);
      rot<true>(x[9], x[1], k.ta[2 * j + 1], k.tb[2 * j + 1]);
      e[p][i] = pack2(x[8], x[9]);
      e[2 + p][i] = pack2(x[0], x[1]);
    }
    stsm4(za ^ (64 * p), e[p]);
    stsm4((za ^ (64 * p)) + 4096, e[2 + p]);
  }
  fence_async_smem();
  wg_sync(1 + wg);
  wg_fence();
  WgRS<64>::set<HI_SW128>(H, k.fi[0], dz);
#pragma unroll
  for (int ks = 1; ks < 4; ks++) WgRS<64>::mma<HI_SW128>(H, k.fi[ks], dz + 128 * ks);
  wg_commit();
  wg_wait<0>();
  pin<32>(H);
  TSIF(w == 0, 88 + c);
#pragma unroll
  for (int j = 0; j < 8; j++)
    a[j >> 2][j & 3] = j < 2 ? pack2(H[4 * j], H[4 * j + 1]) : pack2(H[4 * j] + H[4 * j - 6], H[4 * j + 1] + H[4 * j - 5]);
  stsm4(ya, a[0]);
  stsm4(ya + 2048, a[1]);
  fence_async_smem();
  __syncwarp();
}

__device__ __forceinline__ void prep_slab(uint4* res, const uint2* sw, uint32_t sb, int slab, int w, int lane) {
  const int t = lane & 3, tp = (lane & 7) >> 1, pos = 8 * tp + 2 * (((lane >> 3) + tp) & 3) + (lane & 1);
  const uint32_t base = sb + OFF_KVS + slab * KVS_BYTES + pos * 128;
  uint32_t kk[2][4][4], vv[2][4];
  mbar_wait(sb + OFF_BAR + 8 * (B_KV + slab), 0);
#pragma unroll
  for (int h = 0; h < 2; h++) {
#pragma unroll
    for (int j = 0; j < 4; j++) {
      const uint32_t a = base + 128 * j;
      ldsm4t(kk[h][j], a + (((w + 4 * h) ^ ((a >> 7) & 7)) << 4));
    }
    const uint32_t a = base + KVS_V;
    ldsm4t(vv[h], a + (((w + 4 * h) ^ ((a >> 7) & 7)) << 4));
  }
#pragma unroll
  for (int h = 0; h < 2; h++) {
    uint32_t (&k)[4][4] = kk[h];
    uint32_t (&v)[4] = vv[h];
    const uint32_t w0 = __byte_perm(sw[h].x, 0, 0x1010), w1 = __byte_perm(sw[h].x, 0, 0x3232);
    const uint32_t w2 = __byte_perm(sw[h].y, 0, 0x1010), w3 = __byte_perm(sw[h].y, 0, 0x3232);
#pragma unroll
    for (int m = 0; m < 4; m++)
      v[m] = bmul(badd(badd(badd(bmul(k[0][m], w3), bmul(k[1][m], w2)), bmul(k[2][m], w1)), bmul(k[3][m], w0)), v[m]);
    uint32_t a[4];
#pragma unroll
    for (int m = 0; m < 4; m++) a[m] = (t & 1) ? v[(m + 3) & 3] : v[m];
    res[h] = (t & 2) ? make_uint4(a[2], a[3], a[0], a[1]) : make_uint4(a[0], a[1], a[2], a[3]);
  }
}

__device__ __forceinline__ void prep_gate(const Params& p, int b, int w, int lane) {
  uint2 gw[5], x[4][5];
#pragma unroll
  for (int j = 0; j < 5; j++) gw[j] = ldg64(reinterpret_cast<const uint2*>(p.gate_w) + lane + 32 * j);
#pragma unroll
  for (int i = 0; i < 4; i++)
#pragma unroll
    for (int j = 0; j < 5; j++)
      x[i][j] = ldg64(reinterpret_cast<const uint2*>(p.q) + (16 * b + 4 * w + i) * (DIM / 4) + lane + 32 * j);
  float s[4];
#pragma unroll
  for (int i = 0; i < 4; i++) {
    s[i] = 0.f;
#pragma unroll
    for (int j = 0; j < 5; j++) {
      const uint32_t m0 = bmul(x[i][j].x, gw[j].x), m1 = bmul(x[i][j].y, gw[j].y);
      s[i] += (bf_lo(m0) + bf_hi(m0)) + (bf_lo(m1) + bf_hi(m1));
    }
  }
  const bool h = lane & 16, q = lane & 8;
  const float a = (h ? s[2] : s[0]) + __shfl_xor_sync(0xffffffffu, h ? s[0] : s[2], 16);
  const float c = (h ? s[3] : s[1]) + __shfl_xor_sync(0xffffffffu, h ? s[1] : s[3], 16);
  float z = (q ? c : a) + __shfl_xor_sync(0xffffffffu, q ? a : c, 8);
#pragma unroll
  for (int o = 4; o > 0; o >>= 1) z += __shfl_xor_sync(0xffffffffu, z, o);
  z = bf_lo(pack2(z, 0.f));
  if ((lane & 7) == 0) g_gate[16 * b + 4 * w + (lane >> 3)] = bf_lo(pack2(__fdividef(1.f, 1.f + __expf(-z)), 0.f));
}

__device__ __forceinline__ uint32_t bmax(uint32_t a, uint32_t b) {
  uint32_t d;
  asm("max.bf16x2 %0, %1, %2;" : "=r"(d) : "r"(a), "r"(b));
  return d;
}
__device__ __forceinline__ void softmax_two(const float (&l)[2][2], uint32_t& p0, uint32_t& p1) {
  constexpr float kScale = 0.22360679774997896f, kLog2e = 1.4426950408889634f;
  const uint32_t r0 = pack2(l[0][0], l[1][0]), r1 = pack2(l[0][1], l[1][1]);
  const uint32_t x0 = pack2(bf_lo(r0) * kScale, bf_hi(r0) * kScale), x1 = pack2(bf_lo(r1) * kScale, bf_hi(r1) * kScale);
  uint32_t m = bmax(x0, x1);
  m = bmax(m, __shfl_xor_sync(0xffffffffu, m, 1));
  m = bmax(m, __shfl_xor_sync(0xffffffffu, m, 2));
  const float m0 = bf_lo(m) * kLog2e, m1 = bf_hi(m) * kLog2e;
  p0 = pack2(ex2(bf_lo(x0) * kLog2e - m0), ex2(bf_lo(x1) * kLog2e - m0));
  p1 = pack2(ex2(bf_hi(x0) * kLog2e - m1), ex2(bf_hi(x1) * kLog2e - m1));
}

__device__ __forceinline__ void halo_read(uint32_t (&kpv)[10], uint32_t (&vpv)[10], uint32_t (&tg)[7], const uint4* hp) {
#pragma unroll
  for (int j = 0; j < 7; j++) {
    uint32_t x0, x1, x2;
    asm volatile("ld.relaxed.gpu.global.v4.u32 {%0, %1, %2, %3}, [%4];"
                 : "=r"(x0), "=r"(x1), "=r"(x2), "=r"(tg[j]) : "l"(hp + 32 * j) : "memory");
    if (j < 4) kpv[3 * j] = x0; else vpv[3 * j - 10] = x0;
    if (j < 3) kpv[3 * j + 1] = x1; else vpv[3 * j - 9] = x1;
    if (j < 3) kpv[3 * j + 2] = x2; else if (j < 6) vpv[3 * j - 8] = x2;
  }
}

template <int ROT>
__device__ __forceinline__ void pack_qkv(const float* acc, uint32_t (&qlo)[10], uint32_t (&qhi)[10], uint32_t (&klo)[10],
                                         uint32_t (&khi)[10], uint32_t (&vlo)[10], uint32_t (&vhi)[10]) {
#pragma unroll
  for (int j = 0; j < 10; j++) {
    const int x = (j + ROT) % 10, tq = x < 8 ? x : 16 + x, tk = x < 8 ? 8 + x : 18 + x, tv = x < 8 ? 16 + x : 20 + x;
    khi[j] = pack2(acc[4 * tk + 2], acc[4 * tk + 3]);
    vhi[j] = movm(pack2(acc[4 * tv + 2], acc[4 * tv + 3]));
    qlo[j] = pack2(acc[4 * tq], acc[4 * tq + 1]);
    qhi[j] = pack2(acc[4 * tq + 2], acc[4 * tq + 3]);
    klo[j] = pack2(acc[4 * tk], acc[4 * tk + 1]);
    vlo[j] = pack2(acc[4 * tv], acc[4 * tv + 1]);
    asm volatile("" : "+r"(khi[j]), "+r"(qlo[j]), "+r"(qhi[j]), "+r"(klo[j]), "+r"(vlo[j]));
  }
}

__device__ __forceinline__ void attention(float* acc, uint32_t sb, int b, int par, int w, int lane) {
  const int g = lane >> 2, t = lane & 3;
  uint32_t klo[10], khi[10], vlo[10], vhi[10], qlo[10], qhi[10], kpv[10], vpv[10];
  if (tail_first(b & 7)) pack_qkv<8>(acc, qlo, qhi, klo, khi, vlo, vhi);
  else pack_qkv<0>(acc, qlo, qhi, klo, khi, vlo, vhi);
  uint32_t tag = 0;
  if (w == 0 || w == 3) {
    mbar_wait(sb + OFF_BAR + 8 * B_EPOCH, 0);
    tag = lds32(sb + OFF_EPOCH) + 1;
  }
  const uint32_t xa = sb + OFF_KVX + (par * 3) * 2560 + lane * 16;
  if (w < 3) {
    mbar_wait(sb + OFF_BAR + 8 * B_S3, 0);
    sts128(xa + w * 2560, khi[0], khi[1], khi[2], khi[3]);
    sts128(xa + w * 2560 + 512, khi[4], khi[5], khi[6], khi[7]);
    sts128(xa + w * 2560 + 1024, khi[8], khi[9], vhi[0], vhi[1]);
    sts128(xa + w * 2560 + 1536, vhi[2], vhi[3], vhi[4], vhi[5]);
    sts128(xa + w * 2560 + 2048, vhi[6], vhi[7], vhi[8], vhi[9]);
  } else if (b < NCTA - 8) {
    uint4* ho = g_halo + (b * 2 + par) * 224 + lane;
#pragma unroll
    for (int j = 0; j < 7; j++) {
      const uint32_t x0 = j < 4 ? khi[3 * j] : vhi[3 * j - 10], x1 = j < 3 ? khi[3 * j + 1] : vhi[3 * j - 9];
      const uint32_t x2 = j < 3 ? khi[3 * j + 2] : j < 6 ? vhi[3 * j - 8] : 0u;
      asm volatile("st.relaxed.gpu.global.v4.u32 [%0], {%1, %2, %3, %4};" ::"l"(ho + 32 * j), "r"(x0), "r"(x1), "r"(x2), "r"(tag) : "memory");
    }
  }
  TSIF(par == 0 && w == 1, 64);
  TSIF(par == 0 && w == 3, 76);
#pragma unroll
  for (int j = 0; j < 10; j++) vlo[j] = movm(vlo[j]);
  const bool far0 = 2 * t > g, far1 = 2 * t + 1 > g;
  const uint32_t mfar = (far0 ? 0x0000FFFFu : 0u) | (far1 ? 0xFFFF0000u : 0u);
  float slo[4][2], shi[4][2], lg[2][2];
  uint32_t phi[4], plo[4], qml[4], qmh[4];
#pragma unroll
  for (int h = 0; h < 4; h++) {
    const int f = h == 0 ? 0 : h == 1 ? 3 : h == 2 ? 5 : 8, hf = h < 2 ? 2 : 7;
    const bool mine = (h & 1) ? t >= 2 : t < 2;
    qml[h] = mine ? qlo[hf] : 0u;
    qmh[h] = mine ? qhi[hf] : 0u;
    float a[4] = {0.f, 0.f, 0.f, 0.f}, c[4] = {0.f, 0.f, 0.f, 0.f};
    mma16816(a, qlo[f], qhi[f], qlo[f + 1], qhi[f + 1], klo[f], klo[f + 1]);
    mma16816(c, qlo[f], qhi[f], qlo[f + 1], qhi[f + 1], khi[f], khi[f + 1]);
    mma1688(a, qml[h], qmh[h], klo[hf]);
    mma1688(c, qml[h], qmh[h], khi[hf]);
    slo[h][0] = a[0];
    slo[h][1] = a[1];
    shi[h][0] = lg[h & 1][0] = far0 ? a[2] : c[2];
    shi[h][1] = lg[h & 1][1] = far1 ? a[3] : c[3];
    if (!ATT_MERGE && (h & 1)) softmax_two(lg, phi[h - 1], phi[h]);
  }
  TSIF(par == 0 && w == 1, 65);
  wg_sync(1 + par);
  TSIF(par == 0 && w == 1, 66);
  const bool nohist = (w == 0) && (b < 8);
  const uint4* hp = g_halo + ((b - 8) * 2 + par) * 224 + lane;
  uint32_t tg[7];
  if (w > 0) {
    const uint4 v0 = lds128(xa + (w - 1) * 2560), v1 = lds128(xa + (w - 1) * 2560 + 512), v2 = lds128(xa + (w - 1) * 2560 + 1024);
    const uint4 v3 = lds128(xa + (w - 1) * 2560 + 1536), v4 = lds128(xa + (w - 1) * 2560 + 2048);
    kpv[0] = v0.x; kpv[1] = v0.y; kpv[2] = v0.z; kpv[3] = v0.w; kpv[4] = v1.x; kpv[5] = v1.y; kpv[6] = v1.z; kpv[7] = v1.w;
    kpv[8] = v2.x; kpv[9] = v2.y; vpv[0] = v2.z; vpv[1] = v2.w; vpv[2] = v3.x; vpv[3] = v3.y; vpv[4] = v3.z; vpv[5] = v3.w;
    vpv[6] = v4.x; vpv[7] = v4.y; vpv[8] = v4.z; vpv[9] = v4.w;
  } else if (nohist) {
#pragma unroll
    for (int j = 0; j < 10; j++) kpv[j] = vpv[j] = 0u;
  } else {
    TSIF(par == 0, 77);
    halo_read(kpv, vpv, tg, hp);
  }
  if (w == 0 && !nohist) {
    int spins = 0;
    while (true) {
      bool ok = true;
#pragma unroll
      for (int j = 0; j < 7; j++) ok = ok && tg[j] == tag;
      if (__all_sync(0xffffffffu, ok) || ++spins > SPIN_LIMIT) break;
      halo_read(kpv, vpv, tg, hp);
    }
    TSIF(par == 0, 79);
  }
#pragma unroll
  for (int h = 0; h < 4; h++) {
    const int f = h == 0 ? 0 : h == 1 ? 3 : h == 2 ? 5 : 8, hf = h < 2 ? 2 : 7;
    float a[4] = {0.f, 0.f, 0.f, 0.f};
    mma16816(a, qlo[f], qhi[f], qlo[f + 1], qhi[f + 1], kpv[f], kpv[f + 1]);
    mma1688(a, qml[h], qmh[h], kpv[hf]);
    const float ninf = __int_as_float(0xff800000);
    lg[h & 1][0] = far0 ? (nohist ? ninf : a[0]) : slo[h][0];
    lg[h & 1][1] = far1 ? (nohist ? ninf : a[1]) : slo[h][1];
    if (h & 1) {
      softmax_two(lg, plo[h - 1], plo[h]);
      if (ATT_MERGE) {
        const float lh[2][2] = {{shi[h - 1][0], shi[h - 1][1]}, {shi[h][0], shi[h][1]}};
        softmax_two(lh, phi[h - 1], phi[h]);
      }
    }
  }
  TSIF(par == 0 && w <= 1, 67 + w);
  uint32_t ov[20];
#pragma unroll
  for (int hp = 0; hp < 2; hp++) {
    const int hf = hp ? 7 : 2;
    float sh[4] = {0.f, 0.f, 0.f, 0.f}, i0 = 0.f, i1 = 0.f;
#pragma unroll
    for (int e = 0; e < 2; e++) {
      const int h = 2 * hp + e, f = h == 0 ? 0 : h == 1 ? 3 : h == 2 ? 5 : 8;
      const uint32_t a0 = plo[h] & mfar, a2 = plo[h] & ~mfar, a3 = phi[h] & mfar, c1 = phi[h] & ~mfar;
      float sum[4] = {0.f, 0.f, 0.f, 0.f};
      mma1688(sum, plo[h], phi[h], 0x3F803F80u);
      const float r0 = rcp(sum[0]), r1 = rcp(sum[2]);
#pragma unroll
      for (int j = f; j < f + 2; j++) {
        float o[4] = {0.f, 0.f, 0.f, 0.f};
        mma16816(o, a0, 0u, a2, a3, vpv[j], vlo[j]);
        mma1688(o, 0u, c1, vhi[j]);
        ov[2 * j] = pack2(o[0] * r0, o[1] * r0);
        ov[2 * j + 1] = pack2(o[2] * r1, o[3] * r1);
      }
      const bool mine = e ? g >= 4 : g < 4;
      mma16816(sh, a0, 0u, a2, a3, mine ? vpv[hf] : 0u, mine ? vlo[hf] : 0u);
      mma1688(sh, 0u, c1, mine ? vhi[hf] : 0u);
      if (e == 0 || t >= 2) {
        i0 = r0;
        i1 = r1;
      }
    }
    ov[2 * hf] = pack2(sh[0] * i0, sh[1] * i0);
    ov[2 * hf + 1] = pack2(sh[2] * i1, sh[3] * i1);
  }
  TS(32 + 4 * par + w);
  mbar_wait(sb + OFF_BAR + 8 * B_P1, 0);
  const uint32_t oa = sb + OFF_OA + (lane >> 4) * 2048 + (32 * w + 2 * (lane & 15) + par) * 16;
#pragma unroll
  for (int j = 0; j < 5; j++) stsm4(oa + 4096 * j, ov + 4 * j);
  TSIF(par == 0 && w == 0, 120);
  fence_async_smem();
  TSIF(par == 0 && w == 0, 121);
  __syncwarp();
  if (lane == 0) mbar_arrive(sb + OFF_BAR + 8 * B_ATTN);
  TSIF(par == 0 && w == 0, 122);
}

struct Maps {
  CUtensorMap x, wm, wt, k, v, y, wo, qm, qt, om, ot;
};

__device__ __forceinline__ void load_stage(uint32_t sb, int kb, int b, const Maps& m) {
  const uint32_t st = sb + (kb & 3) * STAGE_BYTES, bar = sb + OFF_BAR + 8 * (B_FULL1 + (kb & 3));
  const int r = b >> 3, hg = b & 7, slab = kb - KV_KB;
  const bool kv = slab >= 0 && slab < 5;
  const uint32_t kbar = sb + OFF_BAR + 8 * (B_KV + slab), dst = sb + OFF_KVS + slab * KVS_BYTES;
  mbar_expect_tx(bar, STAGE_BYTES);
  if (kv) mbar_expect_tx(kbar, KVS_BYTES);
  tma_3d(st, &m.x, 64 * kb, 64 * r, 0, bar);
  if (kv && KV_MIX) tma_3d(dst, &m.k, 0, 32 * (b >> 1) - 3, 2 * slab + (b & 1), kbar);
  tma_3d(st + ST_W, &m.wm, 80 * hg + (tail_first(hg) ? 16 : 0), 64 * kb, 0, bar);
  if (kv && KV_MIX) tma_3d(dst + KVS_V, &m.v, 0, 32 * (b >> 1), 2 * slab + (b & 1), kbar);
  tma_3d(st + ST_WT, &m.wt, 80 * hg + (tail_first(hg) ? 0 : 64), 64 * kb, 0, bar);
  if (kv && !KV_MIX) tma_3d(dst, &m.k, 0, 32 * (b >> 1) - 3, 2 * slab + (b & 1), kbar);
  if (kv && !KV_MIX) tma_3d(dst + KVS_V, &m.v, 0, 32 * (b >> 1), 2 * slab + (b & 1), kbar);
}

__global__ void __launch_bounds__(NTHR, 1) fused_kernel(const __grid_constant__ Maps m, const Params p) {
  extern __shared__ __align__(1024) uint8_t smem[];
  const uint32_t sb = (uint32_t)__cvta_generic_to_shared(smem);
  const uint32_t bars = sb + OFF_BAR;
  const int tid = threadIdx.x, lane = tid & 31;
  int b = blockIdx.x;
  if (BMAP == 1) b = (((b & 63) >> 3) * 2 + (b & 1)) * 8 + (((b < 64 ? 0x6521 : 0x7430) >> (4 * ((b >> 1) & 3))) & 7);
  if (BMAP == 2) b = ((b & 63) >> 2) * 8 + (((b < 64 ? 0x6521 : 0x7430) >> (4 * (b & 3))) & 7);
  if (BMAP == 3) b = (((b & 63) >> 3) * 2 + (b & 1)) * 8 + (((b < 64 ? 0x7430 : 0x6521) >> (4 * ((b >> 1) & 3))) & 7);
  if (BMAP == 4) b = (((b >> 4) * 2 + (b & 1)) * 8) + ((b >> 1) & 7);
  if (BMAP == 5) b = 127 - b;
  const int r = b >> 3, hg = b & 7;

  if (tid == T_ISSUE) {
    TSM(true, 0);
#pragma unroll
    for (int i = 0; i < 4; i++) mbar_init(bars + 8 * (B_FULL1 + i), 1);
#pragma unroll
    for (int i = 0; i < 3; i++) mbar_init(bars + 8 * (B_KV + i), 1);
    fence_async_smem();
#pragma unroll 1
    for (int kb = 0; kb <= PRE2; kb++) load_stage(sb, kb, b, m);
  } else if (tid >= T_PF && tid < T_PF + 11) {
    tm_prefetch(&m.x + (tid - T_PF));
  } else if (tid == T_INIT) {
#pragma unroll
    for (int i = 0; i < 4; i++) mbar_init(bars + 8 * (B_EMPTY1 + i), 8);
#pragma unroll
    for (int i = 0; i < 8; i++) mbar_init(bars + 8 * (B_FULL2 + i), 1);
#pragma unroll
    for (int i = 0; i < 4; i++) mbar_init(bars + 8 * (B_EMPTY2 + i), 8);
#pragma unroll
    for (int i = 0; i < 4; i++) mbar_init(bars + 8 * (B_U + i), 1);
    mbar_init(bars + 8 * B_HA, 4);
    mbar_init(bars + 8 * B_GATE, 4);
    mbar_init(bars + 8 * B_HB, 1);
    mbar_init(bars + 8 * B_KVD, 4);
    mbar_init(bars + 8 * B_QF, 1);
    mbar_init(bars + 8 * B_ATTN, 8);
    mbar_init(bars + 8 * B_P1, 8);
    mbar_init(bars + 8 * B_C34, 1);
#pragma unroll
    for (int i = 0; i < 5; i++) mbar_init(bars + 8 * (B_YST + i), 4);
#pragma unroll
    for (int i = 0; i < 5; i++) mbar_init(bars + 8 * (B_TOK + i), 4);
    mbar_init(bars + 8 * B_YSIG, 1);
    mbar_init(bars + 8 * B_YFULL, 1);
    mbar_init(bars + 8 * B_EPOCH, 1);
    mbar_init(bars + 8 * B_PREP, 4);
    mbar_init(bars + 8 * B_USIG, 1);
    mbar_init(bars + 8 * B_WST, 1);
#pragma unroll
    for (int i = 3; i < 5; i++) mbar_init(bars + 8 * (B_KV + i), 1);
    mbar_init(bars + 8 * B_E3, 8);
    mbar_init(bars + 8 * B_LAST, 1);
    mbar_init(bars + 8 * B_OSIG, 1);
    mbar_init(bars + 8 * B_WOP, 1);
    fence_async_smem();
  }
  const int warp = __shfl_sync(0xffffffffu, tid >> 5, 0), wg = warp >> 2, w = warp & 3;
  __syncthreads();

  if (wg == 3) {
    asm volatile("setmaxnreg.dec.sync.aligned.u32 56;");
    if (w == 0) {
      if (lane == 0) {
#pragma unroll 1
        for (int kb = 1 + PRE2; kb < 10; kb++) {
          if (kb >= 4) mbar_wait(bars + 8 * (kb == 7 ? B_E3 : B_EMPTY1 + (kb & 3)), (kb >> 3) & 1);
          TSIF(kb >= 4, 44 + kb);
          load_stage(sb, kb, b, m);
          if (kb == TRIG_KB) mbar_arrive(bars + 8 * B_LAST);
        }
        mbar_wait(bars + 8 * B_WOP, 0);
        flag_wait(g_cnt + C_W + 32 * hg, (lds32(sb + OFF_EPOCH) + 1) * 16);
        TS(30);
#pragma unroll 1
        for (int j = 0; j < 8; j++) {
          if (j >= 6) mbar_wait(bars + 8 * (B_EMPTY2 + j - 6), 0);
          TSIF(j >= 6, 100 + j);
          if (RF_GATE && j == 6) mbar_wait(bars + 8 * B_YSIG, 0);
          mbar_expect_tx(bars + 8 * (B_FULL2 + j), j == 0 ? WO_BYTES : j == 5 ? O_BYTES + WO_BYTES + 512 : O_BYTES + WO_BYTES);
          bulk_load(sb + off_w(j), g_WO + (hg * 8 + step_src(hg, j)) * 800, WO_BYTES, bars + 8 * (B_FULL2 + j));
        }
        mbar_wait(bars + 8 * (B_EMPTY2 + 3), 0);
        mbar_expect_tx(bars + 8 * B_QF, O_BYTES);
        tma_2d(sb + OFF_QS, &m.qm, 80 * hg, 128 * r, bars + 8 * B_QF);
        tma_2d(sb + OFF_QT, &m.qt, 80 * hg + 64, 128 * r, bars + 8 * B_QF);
      }
    } else if (w == 1) {
      unsigned epoch = 0;
      if (lane == 0) {
        epoch = atomicAdd(g_cnt + C_LAUNCH, 1u) / NCTA;
        asm volatile("st.shared.u32 [%0], %1;" ::"r"(sb + OFF_EPOCH), "r"(epoch) : "memory");
        mbar_arrive(bars + 8 * B_EPOCH);
        mbar_wait(bars + 8 * B_KVD, 0);
        mbar_expect_tx(bars + 8 * B_HB, 5 * 4096);
#pragma unroll 1
        for (int c = 0; c < 5; c++) {
          if (c == 3) mbar_wait(bars + 8 * B_S3, 0);
          bulk_load(sb + off_ch(c) + U_BYTES, p.ssm_k + (5 * b + c) * SEQ, 4096, bars + 8 * B_HB);
        }
#pragma unroll
        for (int c = 0; c < 4; c++) mbar_expect_tx(bars + 8 * (B_U + c), c < 3 ? U_BYTES : 2 * U_BYTES);
        const uint4* usrc = g_U + 5 * b * U_PITCH;
        mbar_wait(bars + 8 * B_USIG, 0);
        flag_wait(g_cnt + C_PREP + 32 * (b & 15), (epoch + 1) * NCTA);
        TS(23);
#pragma unroll
        for (int c = 0; c < 5; c++) {
          if (c == 3) mbar_wait(bars + 8 * (B_U + 2), 0);
          bulk_load(sb + off_ch(c), usrc + c * U_PITCH, U_BYTES, bars + 8 * (B_U + (c < 3 ? c : 3)));
          TSIF(c == 0 || c == 4, 116 + (c >> 2));
        }
      }
      epoch = __shfl_sync(0xffffffffu, epoch, 0);
      if (lane < 8) {
        const int src = (b & ~7) | step_src(hg, lane);
        mbar_wait(bars + 8 * B_OSIG, 0);
        flag_wait(g_cnt + C_O + 32 * src, epoch + 1);
        if (lane >= 1 && lane < 4) bulk_load(sb + off_o(lane), g_O + src * 1280, O_BYTES, bars + 8 * (B_FULL2 + lane));
        __syncwarp(0xff);
        TS(21);
        if (lane == 5) bulk_load(sb + OFF_GATE, g_gate + 128 * r, 512, bars + 8 * (B_FULL2 + 5));
#pragma unroll 1
        for (int j = 4; j < 8; j++) {
          if (lane == j) {
            mbar_wait(bars + 8 * (j < 6 ? B_C34 : B_EMPTY2 + j - 6), 0);
            if (RF_GATE && j == 6) mbar_wait(bars + 8 * B_YSIG, 0);
            bulk_load(sb + off_o(j), g_O + src * 1280, O_BYTES, bars + 8 * (B_FULL2 + j));
          }
          __syncwarp(0xff);
        }
        TS(22);
      }
    } else if (w == 2) {
      mbar_wait(bars + 8 * B_PREP, 0);
      flag_signal(g_cnt + C_PREP, 16, lane);
      TS(25);
      if (lane == 0) mbar_arrive(bars + 8 * B_USIG);
      mbar_wait(bars + 8 * B_GATE, 0);
      mbar_wait(bars + 8 * B_ATTN, 0);
      if (lane == 0) {
        if (O_DEFER) mbar_wait(bars + 8 * (B_U + 3), 0);
        asm volatile("cp.async.bulk.global.shared::cta.bulk_group [%0], [%1], 20480;\ncp.async.bulk.commit_group;\n"
                     "cp.async.bulk.wait_group 0;\nfence.proxy.async.global;" ::"l"(g_O + b * 1280), "r"(sb + OFF_OA) : "memory");
      }
      flag_signal(g_cnt + C_O + 32 * b, 1, lane);
      TS(26);
      if (lane == 0) mbar_arrive(bars + 8 * B_OSIG);
      mbar_wait(bars + 8 * B_WOP, 0);
      flag_signal(g_cnt + C_W + 32 * hg, 1, lane);
      TS(73);
    } else {
      if (lane == 0) {
        mbar_wait(bars + 8 * WB_TRIG, 0);
        mbar_expect_tx(bars + 8 * B_WST, WO_BYTES / 2);
        tma_3d(sb + OFF_WA, &m.wo, 0, 40 * r, 5 * hg, bars + 8 * B_WST);
        mbar_wait(bars + 8 * B_WST, 0);
        mbar_wait(bars + 8 * WO_TRIG, 0);
        uint4* dst = g_WO + (hg * 8 + (r >> 1)) * 800 + (r & 1) * 80;
#pragma unroll 1
        for (int n = 0; n < 5; n++)
          asm volatile("cp.async.bulk.global.shared::cta.bulk_group [%0], [%1], 1280;" ::"l"(dst + 160 * n), "r"(sb + OFF_WA + 1280 * n) : "memory");
        asm volatile("cp.async.bulk.commit_group;\ncp.async.bulk.wait_group 0;\nfence.proxy.async.global;" ::: "memory");
        mbar_arrive(bars + 8 * B_WOP);
      }
      TS(71);
      if (lane == 0) {
#pragma unroll 1
        for (int c = 0; c < 5; c++) {
          mbar_wait(bars + 8 * (B_YST + c), 0);
          asm volatile("cp.async.bulk.global.shared::cta.bulk_group [%0], [%1], 4096;\ncp.async.bulk.commit_group;"
                       ::"l"(g_Y + (5 * b + c) * Y_PITCH), "r"(sb + off_ch(c)) : "memory");
          if (c == 2) {
            asm volatile("cp.async.bulk.wait_group.read 0;" ::: "memory");
            mbar_arrive(bars + 8 * B_C34);
          }
        }
        asm volatile("cp.async.bulk.wait_group 0;\nfence.proxy.async.global;\nred.release.gpu.global.add.u32 [%0], 1;"
                     ::"l"(g_cnt + C_Y + 32 * (b >> 4)) : "memory");
        TS(27);
        mbar_arrive(bars + 8 * B_YSIG);
        mbar_expect_tx(bars + 8 * B_YFULL, 20480);
        flag_wait(g_cnt + C_Y + 32 * hg, (lds32(sb + OFF_EPOCH) + 1) * 16);
        TS(24);
        tma_2d(sb + OFF_YT, &m.y, 128 * r, 80 * hg, bars + 8 * B_YFULL);
        tma_2d(sb + OFF_YT + 10240, &m.y, 128 * r + 64, 80 * hg, bars + 8 * B_YFULL);
      }
    }
  } else {
    asm volatile("setmaxnreg.inc.sync.aligned.u32 152;");
    if (wg < 2) {
      float acc[120];
#pragma unroll
      for (int i = 0; i < 120; i++) acc[i] = 0.f;
      const uint32_t da = desc_lo(sb + wg * 8192, 16), db = desc_lo(sb + ST_W, 8192), dc = desc_lo(sb + ST_WT, 2048);
      if (PW1) pin<120>(acc);
      if (PW1 == 2) mbar_wait(bars + 8 * B_FULL1, 0);
#pragma unroll 1
      for (int kb = 0; kb < 10; kb++) {
        mbar_wait(bars + 8 * (B_FULL1 + (kb & 3)), (kb >> 2) & 1);
        const uint32_t so = (kb & 3) * (STAGE_BYTES >> 4);
        wg_fence();
#pragma unroll
        for (int k = 0; k < 4; k++) {
          WgSST<192>::mma<HI_SW128, HI_SW128>(acc, da + so + 2 * k, db + so + 128 * k, 1);
          WgSST<48>::mma<HI_SW128, HI_SW32>(acc + 96, da + so + 2 * k, dc + so + 32 * k, 1);
        }
        wg_commit();
        wg_wait<1>();
        if (kb > 0 && lane == 0) mbar_arrive(bars + 8 * (kb == 4 ? B_E3 : B_EMPTY1 + ((kb - 1) & 3)));
      }
      wg_wait<0>();
      pin<120>(acc);
      if (lane == 0) mbar_arrive(bars + 8 * B_P1);
      TSM(w == 0, 3 + wg);
      attention(acc, sb, b, wg, w, lane);
    } else {
      const int tw = tid & 127, chl = 64 * (b & 1) + 8 * w + (lane >> 2);
      uint4* up = g_U + chl * U_PITCH + ((4 * (b >> 1) + (lane & 3)) ^ ((b >> 2) & 1));
      uint2 sw[10];
      uint32_t dv = 0;
      if (lane < 5) dv = __ldg(reinterpret_cast<const unsigned short*>(p.ssm_D) + 5 * b + lane);
#pragma unroll
      for (int i = 0; i < 10; i++) sw[i] = ldg64(reinterpret_cast<const uint2*>(p.shift_k) + chl + 128 * (i >> 1) + 32 * (i & 1));
      uint32_t tab[12];
      fft_tables(tab, tw);
      uint4 res[10];
#pragma unroll
      for (int i = 0; i < 10; i++) res[i] = make_uint4(0, 0, 0, 0);
#pragma unroll 1
      for (int slab = 0; slab < 5; slab++) {
#pragma unroll
        for (int i = 0; i < 8; i++) res[i] = res[i + 2];
        prep_slab(res + 8, sw, sb, slab, w, lane);
        TSIF(w == 0, 99 + 4 * slab);
#pragma unroll
        for (int i = 0; i < 8; i++) sw[i] = sw[i + 2];
      }
      TSIF(w == 0, 28);
      __syncwarp();
      if (lane == 0) mbar_arrive(bars + 8 * B_KVD + ((res[8].x ^ res[9].x) & p.zero));
      mbar_wait(bars + 8 * B_KVD, 0);
      fft_tables_store(tab, sb, tw);
      mbar_wait(bars + 8 * B_LAST, 0);
#pragma unroll
      for (int i = 0; i < 10; i++) up[(128 * (i >> 1) + 32 * (i & 1)) * U_PITCH] = res[i];
      __syncwarp();
      if (lane == 0) mbar_arrive(bars + 8 * B_PREP);
      TSIF(w == 0, 5);
      mbar_wait(bars + 8 * (G_AFTER ? B_USIG : B_LAST), 0);
      prep_gate(p, b, w, lane);
      __syncwarp();
      if (lane == 0) mbar_arrive(bars + 8 * B_GATE);
      TSIF(w == 0, 72);
      mbar_wait(bars + 8 * B_HB, 0);
      TSIF(w == 0, 123);
      const uint32_t ha = sb + U_BYTES + ((tw >> 3) * 16 + 8 + (tw & 7)) * 16;
      uint4 hv[5];
#pragma unroll
      for (int c = 0; c < 5; c++) hv[c] = lds128(ha + off_ch(c));
      __syncwarp();
#pragma unroll
      for (int c = 0; c < 5; c++) sts128((ha ^ 16) + off_ch(c), hv[c].x, hv[c].y, hv[c].z, hv[c].w);
      if (tw < 5) asm volatile("st.shared.f32 [%0], %1;" ::"r"(sb + OFF_D + 4 * tw), "f"(bf_lo(dv) * 0.125f) : "memory");
      fence_async_smem();
      __syncwarp();
      if (lane == 0) mbar_arrive(bars + 8 * B_HA);
      TSIF(w == 0, 6);
    }

    FftConst fc;
    fft_twiddles(fc, w, lane);
    mbar_wait(bars + 8 * B_HA, 0);
    fft_matrices(fc, sb, w, lane);
    if (ATT_GATE && !H_EARLY) mbar_wait(bars + 8 * B_ATTN, 0);
    TSIF(w == 0 && wg == 2, 124);
#pragma unroll 1
    for (int c = wg == 2 ? 0 : wg + 1; c < 5; c += 3) {
      conv_channel(fc, sb, c, wg, w, lane);
      if (lane == 0) mbar_arrive(bars + 8 * (B_YST + c));
      TSM(w == 0, 10 + c);
    }

    if (wg < 2) {
      const int g = lane >> 2;
      float acc[40];
#pragma unroll
      for (int i = 0; i < 40; i++) acc[i] = 0.f;
      const uint32_t da = desc_lo(sb + wg * 1024, 2048), db = desc_lo(sb, 2560);
      mbar_wait(bars + 8 * B_ATTN, 0);
      mbar_wait(bars + 8 * (B_YST + 3), 0);
      mbar_wait(bars + 8 * (B_YST + 4), 0);
      if (PW2) mbar_wait(bars + 8 * B_FULL2, 0);
#pragma unroll 1
      for (int j = 0; j < 8; j++) {
        mbar_wait(bars + 8 * (B_FULL2 + j), 0);
        const uint32_t oa = da + (off_o(j) >> 4), ob = db + (off_w(j) >> 4);
        wg_fence();
#pragma unroll
        for (int k = 0; k < 5; k++) WgSST<80>::mma<HI_NONE, HI_SW32>(acc, oa + 256 * k, ob + 32 * k, 1);
        wg_commit();
        wg_wait<1>();
        if (j >= 1 && j <= 4 && lane == 0) mbar_arrive(bars + 8 * (B_EMPTY2 + j - 1));
      }
      TSIF(w == 0 && wg == 0, 113);
      const int tr = 64 * wg + 16 * w + (lane & 15);
      const uint32_t fm = sb + OFF_QS + tr * 128, fx = (lane >> 4) ^ (tr & 7);
      const uint32_t ft = sb + OFF_QT + tr * 32 + (((lane >> 4) ^ (tr >> 2)) & 1) * 16;
      const float g0 = __uint_as_float(lds32(sb + OFF_GATE + (64 * wg + 16 * w + g) * 4));
      const float g1 = __uint_as_float(lds32(sb + OFF_GATE + (64 * wg + 16 * w + 8 + g) * 4));
      const uint32_t ga = pack2(g0, g0), gb = pack2(g1, g1);
      const uint32_t na = pack2(1.f - g0, 1.f - g0), nb = pack2(1.f - g1, 1.f - g1);

      wg_wait<0>();
      pin<40>(acc);
      TSM(w == 0, 17 + wg);
      uint32_t pb[20];
#pragma unroll
      for (int j = 0; j < 10; j++) {
        pb[2 * j] = bmul(na, pack2(acc[4 * j], acc[4 * j + 1]));
        pb[2 * j + 1] = bmul(nb, pack2(acc[4 * j + 2], acc[4 * j + 3]));
        asm volatile("" : "+r"(pb[2 * j]), "+r"(pb[2 * j + 1]));
      }
      const uint32_t ya = sb + OFF_YT + wg * 10240 + ((lane >> 4) * 8 + (lane & 7)) * 128 +
                          (((2 * w + (((lane >> 3) & 1) ^ wg)) ^ (lane & 7)) << 4);
      uint32_t qf[20];
      mbar_wait(bars + 8 * B_QF, 0);
#pragma unroll
      for (int j = 0; j < 5; j++) ldsm4(qf + 4 * j, j < 4 ? fm + ((fx ^ (2 * j)) << 4) : ft);
      mbar_wait(bars + 8 * B_YFULL, 0);
      TSIF(w == 0 && wg == 0, 19);
#pragma unroll
      for (int j = 0; j < 5; j++) {
        uint32_t y[4];
        ldsm4t(y, ya + 2048 * j);
#pragma unroll
        for (int i = 0; i < 4; i++) qf[4 * j + i] = badd(bmul((i & 1) ? gb : ga, bmul(qf[4 * j + i], y[i])), pb[4 * j + i]);
      }
#pragma unroll
      for (int j = 0; j < 5; j++) stsm4(j < 4 ? fm + ((fx ^ (2 * j)) << 4) : ft, qf + 4 * j);
      fence_async_smem();
      __syncwarp();
      if (lane == 0) {
        const int row = 64 * wg + 16 * w;
        asm volatile("cp.async.bulk.tensor.2d.global.shared::cta.bulk_group [%0, {%2, %3}], [%1];"
                     ::"l"(&m.om), "r"(sb + OFF_QS + row * 128), "r"(80 * hg), "r"(128 * r + row) : "memory");
        asm volatile("cp.async.bulk.tensor.2d.global.shared::cta.bulk_group [%0, {%2, %3}], [%1];"
                     ::"l"(&m.ot), "r"(sb + OFF_QT + row * 32), "r"(80 * hg + 64), "r"(128 * r + row) : "memory");
        asm volatile("cp.async.bulk.commit_group;\ncp.async.bulk.wait_group.read 0;" ::: "memory");
      }
      TSM(true, 40 + 4 * wg + w);
      if (ENDBAR) asm volatile("bar.sync 15, 256;" ::: "memory");
    }
  }
}

typedef CUresult (*EncodeFn)(CUtensorMap*, CUtensorMapDataType, cuuint32_t, void*, const cuuint64_t*, const cuuint64_t*,
                             const cuuint32_t*, const cuuint32_t*, CUtensorMapInterleave, CUtensorMapSwizzle,
                             CUtensorMapL2promotion, CUtensorMapFloatOOBfill);

void encode(EncodeFn fn, CUtensorMap* tm, const void* base, int rank, const cuuint64_t* dims, const cuuint64_t* strides,
            const cuuint32_t* box, CUtensorMapSwizzle swz) {
  const cuuint32_t ones[3] = {1, 1, 1};
  fn(tm, CU_TENSOR_MAP_DATA_TYPE_BFLOAT16, rank, const_cast<void*>(base), dims, strides, box, ones,
     CU_TENSOR_MAP_INTERLEAVE_NONE, swz, CU_TENSOR_MAP_L2_PROMOTION_L2_128B, CU_TENSOR_MAP_FLOAT_OOB_FILL_NONE);
}

}

extern "C" void kernel_launch(void* const* d_in, const int* in_sizes, int n_in, void* d_out, int out_size) {
  (void)in_sizes; (void)n_in; (void)out_size;
  Params p;
  p.q = (const __nv_bfloat16*)d_in[0];
  p.k = (const __nv_bfloat16*)d_in[1];
  p.v = (const __nv_bfloat16*)d_in[2];
  p.shift_k = (const __nv_bfloat16*)d_in[3];
  p.ssm_k = (const __nv_bfloat16*)d_in[4];
  p.ssm_D = (const __nv_bfloat16*)d_in[5];
  p.wqkv = (const __nv_bfloat16*)d_in[7];
  p.wo = (const __nv_bfloat16*)d_in[8];
  p.gate_w = (const __nv_bfloat16*)d_in[9];
  p.out = (__nv_bfloat16*)d_out;
  p.zero = 0;

  static EncodeFn fn = nullptr;
  static void* yaddr = nullptr;
  if (!fn) {
    cudaDriverEntryPointQueryResult qr;
    void* f = nullptr;
    cudaGetDriverEntryPoint("cuTensorMapEncodeTiled", &f, cudaEnableDefault, &qr);
    fn = (EncodeFn)f;
    cudaGetSymbolAddress(&yaddr, g_Y);
    cudaFuncSetAttribute(fused_kernel, cudaFuncAttributeMaxDynamicSharedMemorySize, SMEM_BYTES);
  }
  Maps m;
  {
    const cuuint64_t dims[3] = {640, 1024, 2}, st[2] = {2560, 1280};
    const cuuint32_t box[3] = {64, 64, 2};
    encode(fn, &m.x, p.q, 3, dims, st, box, CU_TENSOR_MAP_SWIZZLE_128B);
  }
  {
    const cuuint64_t dims[3] = {640, 640, 3}, st[2] = {3840, 1280};
    const cuuint32_t box[3] = {64, 64, 3}, boxt[3] = {16, 64, 3};
    encode(fn, &m.wm, p.wqkv, 3, dims, st, box, CU_TENSOR_MAP_SWIZZLE_128B);
    encode(fn, &m.wt, p.wqkv, 3, dims, st, boxt, CU_TENSOR_MAP_SWIZZLE_32B);
  }
  {
    const cuuint64_t dims[3] = {64, 2048, 10}, st[2] = {1280, 128};
    const cuuint32_t boxk[3] = {64, 35, 1}, boxv[3] = {64, 32, 1};
    encode(fn, &m.k, p.k, 3, dims, st, boxk, CU_TENSOR_MAP_SWIZZLE_128B);
    encode(fn, &m.v, p.v, 3, dims, st, boxv, CU_TENSOR_MAP_SWIZZLE_128B);
  }
  {
    const cuuint64_t dims[3] = {16, 640, 40}, st[2] = {1280, 32};
    const cuuint32_t box[3] = {16, 40, 5};
    encode(fn, &m.wo, p.wo, 3, dims, st, box, CU_TENSOR_MAP_SWIZZLE_32B);
  }
  {
    const cuuint64_t dims[2] = {2048, 640}, st[1] = {Y_PITCH * 16};
    const cuuint32_t box[2] = {64, 80};
    encode(fn, &m.y, yaddr, 2, dims, st, box, CU_TENSOR_MAP_SWIZZLE_128B);
  }
  {
    const cuuint64_t dims[2] = {640, 2048}, st[1] = {1280};
    const cuuint32_t bqm[2] = {64, 128}, bqt[2] = {16, 128}, bom[2] = {64, 16}, bot[2] = {16, 16};
    encode(fn, &m.qm, p.q, 2, dims, st, bqm, CU_TENSOR_MAP_SWIZZLE_128B);
    encode(fn, &m.qt, p.q, 2, dims, st, bqt, CU_TENSOR_MAP_SWIZZLE_32B);
    encode(fn, &m.om, p.out, 2, dims, st, bom, CU_TENSOR_MAP_SWIZZLE_128B);
    encode(fn, &m.ot, p.out, 2, dims, st, bot, CU_TENSOR_MAP_SWIZZLE_32B);
  }
  fused_kernel<<<NCTA, NTHR, SMEM_BYTES>>>(m, p);
}
```

```cpp
#include <cuda.h>
#include <cuda_bf16.h>
#include <cuda_runtime.h>
#include <stdint.h>

namespace {

constexpr int SEQ = 2048, DIM = 640, NCTA = 128, NTHR = 512;

#define TRIG_KB 9
#define KV_KB 2
#define DEV_EXIT 0
#define ATT_GATE 1
#define G_AFTER 0
#define FENCE_LO 0
#define FENCE_HI 0
#define PW1 2
#define PW2 1
#define ENDBAR 0
#define PAD_KB 0
#define Y_ALIAS 1
#define H_EARLY 1
#define NOMB 7
#define WO_EARLY 2
#define SRC_ROT 0
#define WAIT_NS 0
#define WB_TRIG B_ATTN
#define G_POS 0
#define TAILF 1
#define T_ISSUE 384
#define T_PF 416
#define T_INIT 448
#define ATT_MERGE 0
#define BMAP 1
#define PRE2 1
#define KV_MIX 0
#define O_DEFER 0
#define TOK_G 1
#define RF_GATE 0
#define WO_TRIG B_OSIG
#define WL_TRIG B_P1
#define WO_GATE 1

constexpr uint32_t STAGE_BYTES = 47104, ST_W = 16384, ST_WT = 40960;
constexpr uint32_t O_BYTES = 20480, WO_BYTES = 12800;
constexpr uint32_t OFF_OA = 0;
constexpr uint32_t OFF_QS = 3 * O_BYTES, OFF_QT = OFF_QS + 16384;
constexpr uint32_t OFF_WC = 81920;
constexpr uint32_t OFF_WA = 94720;
constexpr uint32_t OFF_GATE = 145920;
constexpr uint32_t OFF_KVX = 147968;
constexpr uint32_t OFF_D = OFF_GATE + 512;
constexpr uint32_t OFF_CH3 = 163840;
constexpr uint32_t CH_BYTES = 12288, U_BYTES = 4096;
constexpr uint32_t OFF_FT = 225280, OFF_GT = 229376;
constexpr uint32_t OFF_CH0 = 188416;
constexpr uint32_t OFF_KVS = OFF_CH0, KVS_V = 4480, KVS_BYTES = 8576;
constexpr uint32_t OFF_WS = WO_EARLY ? OFF_KVS + 4 * KVS_BYTES : OFF_WA;
constexpr uint32_t OFF_YT = 163840;
constexpr uint32_t OFF_BAR = 231936;
constexpr uint32_t SMEM_BYTES = OFF_BAR + 512;

enum : uint32_t {
  B_FULL1 = 0, B_EMPTY1 = 4, B_S3 = 7, B_FULL2 = 52, B_EMPTY2 = 13, B_U = 8, B_GATE = 12, B_HA = 19, B_HB = 20,
  B_ATTN = 21, B_C34 = 22, B_CONV = 23, B_YFULL = 24, B_EPOCH = 25, B_PREP = 26, B_P1 = 27, B_LAST = 28,
  B_E3 = 29, B_OSIG = 30, B_WOP = 31, B_USIG = 32, B_WST = 33, B_KV = 34, B_KVD = 39, B_HC = 61, B_QF = 62, B_YST = 40,
  B_TOK = 45, B_YSIG = 50
};
constexpr uint32_t OFF_EPOCH = OFF_BAR + 8 * 51;
__device__ __forceinline__ uint32_t off_o(int j) { return j < 4 ? OFF_OA + j * O_BYTES : j < 6 ? OFF_CH0 + (j - 4) * O_BYTES : OFF_OA + (j - 6) * O_BYTES; }
__device__ __forceinline__ uint32_t off_w(int j) { return j < 4 ? OFF_WA + j * WO_BYTES : j == 4 ? OFF_KVX : j == 5 ? OFF_WC : OFF_WA + (j - 6) * WO_BYTES; }
__device__ __forceinline__ int step_src(int hg, int j) { return SRC_ROT ? (hg + j) & 7 : j == 0 ? hg : j <= hg ? j - 1 : j; }
__device__ __forceinline__ bool tail_first(int hg) { return TAILF && (hg & 3) == 3; }
__device__ __forceinline__ uint32_t off_ch(int c) { return (c < 3 ? OFF_CH0 : OFF_CH3 - 3 * CH_BYTES) + c * CH_BYTES; }

#define U_PITCH 264
__device__ __align__(1024) uint4 g_U[DIM * U_PITCH];
__device__ uint4 g_O[NCTA * 1280];
#define g_Y g_U
constexpr int Y_PITCH = U_PITCH;
__device__ uint4 g_WO[64 * 800];
__device__ uint4 g_halo[NCTA * 2 * 7 * 32];
__device__ float g_gate[SEQ + PAD_KB * 256];
__device__ unsigned g_cnt[32 * (1 + 2 * 16 + 8 + NCTA)];
constexpr int C_LAUNCH = 0, C_PREP = 32, C_Y = 32 * 17, C_W = 32 * 33, C_O = 32 * 41;

#define TSM(cond, slot) do { } while (0)
#define TSIF(cond, slot) do { if (__LINE__ >= FENCE_LO && __LINE__ < FENCE_HI) sched_fence(); } while (0)
__device__ __forceinline__ void sched_fence() {
  asm volatile("{\n.reg .pred p;\n.reg .u32 c;\nmov.u32 c, %%clock;\nsetp.eq.u32 p, c, 0;\n@p st.shared.u32 [%0], c;\n}"
               ::"r"(1024 + OFF_EPOCH + 4) : "memory");
}
#define TS(slot) TSIF(true, slot)

struct Params {
  const __nv_bfloat16 *q, *k, *v, *shift_k, *ssm_k, *ssm_D, *wqkv, *wo, *gate_w;
  __nv_bfloat16* out;
  uint32_t zero;
};

#define POLL_NS 0
constexpr int SPIN_LIMIT = 1 << 17;

__device__ __forceinline__ void mbar_init(uint32_t bar, uint32_t count) {
  asm volatile("mbarrier.init.shared::cta.b64 [%0], %1;" ::"r"(bar), "r"(count) : "memory");
}
__device__ __forceinline__ void mbar_expect_tx(uint32_t bar, uint32_t bytes) {
  asm volatile("mbarrier.arrive.expect_tx.shared::cta.b64 _, [%0], %1;" ::"r"(bar), "r"(bytes) : "memory");
}
__device__ __forceinline__ void mbar_arrive(uint32_t bar) {
  asm volatile("mbarrier.arrive.shared::cta.b64 _, [%0];" ::"r"(bar) : "memory");
}
__device__ __forceinline__ void mbar_wait(uint32_t bar, uint32_t parity) {
  uint32_t ok;
  int spins = 0;
  do {
    if (WAIT_NS)
      asm volatile("{\n.reg .pred p;\nmbarrier.try_wait.parity.shared::cta.b64 p, [%1], %2, %3;\nselp.b32 %0, 1, 0, p;\n}"
                   : "=r"(ok) : "r"(bar), "r"(parity), "r"(WAIT_NS) : "memory");
    else
      asm volatile("{\n.reg .pred p;\nmbarrier.try_wait.parity.shared::cta.b64 p, [%1], %2;\nselp.b32 %0, 1, 0, p;\n}"
                   : "=r"(ok) : "r"(bar), "r"(parity) : "memory");
    if (++spins > SPIN_LIMIT) break;
  } while (!ok);
}
__device__ __forceinline__ void flag_poll(const unsigned* p, unsigned target) {
  unsigned v;
  int spins = 0;
  do {
    if (POLL_NS && spins) __nanosleep(POLL_NS);
    asm volatile("ld.relaxed.gpu.global.u32 %0, [%1];" : "=r"(v) : "l"(p) : "memory");
    if (++spins > SPIN_LIMIT) break;
  } while ((int)(v - target) < 0);
}
__device__ __forceinline__ void flag_wait(const unsigned* p, unsigned target) {
  flag_poll(p, target);
  asm volatile("fence.acquire.gpu;\nfence.proxy.async.global;" ::: "memory");
}
__device__ __forceinline__ void flag_signal(unsigned* p, int n, int lane) {
  if (lane == 0) asm volatile("fence.release.gpu;" ::: "memory");
  __syncwarp();
  if (lane < n) asm volatile("red.relaxed.gpu.global.add.u32 [%0], 1;" ::"l"(p + 32 * lane) : "memory");
}
__device__ __forceinline__ void flag_bump(unsigned* p) {
  asm volatile("red.relaxed.gpu.global.add.u32 [%0], 1;" ::"l"(p) : "memory");
}
__device__ __forceinline__ void fence_async_smem() { asm volatile("fence.proxy.async.shared::cta;" ::: "memory"); }
__device__ __forceinline__ void wg_sync(int id) { asm volatile("bar.sync %0, 128;" ::"r"(id) : "memory"); }

__device__ __forceinline__ void tma_2d(uint32_t dst, const CUtensorMap* tm, int c0, int c1, uint32_t bar) {
  asm volatile("cp.async.bulk.tensor.2d.shared::cluster.global.mbarrier::complete_tx::bytes [%0], [%1, {%3, %4}], [%2];"
               ::"r"(dst), "l"(tm), "r"(bar), "r"(c0), "r"(c1) : "memory");
}
__device__ __forceinline__ void tma_3d(uint32_t dst, const CUtensorMap* tm, int c0, int c1, int c2, uint32_t bar) {
  asm volatile("cp.async.bulk.tensor.3d.shared::cluster.global.mbarrier::complete_tx::bytes [%0], [%1, {%3, %4, %5}], [%2];"
               ::"r"(dst), "l"(tm), "r"(bar), "r"(c0), "r"(c1), "r"(c2) : "memory");
}
__device__ __forceinline__ void bulk_load(uint32_t dst, const void* src, uint32_t bytes, uint32_t bar) {
  asm volatile("cp.async.bulk.shared::cluster.global.mbarrier::complete_tx::bytes [%0], [%1], %2, [%3];"
               ::"r"(dst), "l"(src), "r"(bytes), "r"(bar) : "memory");
}
__device__ __forceinline__ void tm_prefetch(const CUtensorMap* tm) {
  asm volatile("prefetch.tensormap [%0];" ::"l"(tm) : "memory");
}

__device__ __forceinline__ void wg_fence() { asm volatile("wgmma.fence.sync.aligned;" ::: "memory"); }
__device__ __forceinline__ void wg_commit() { asm volatile("wgmma.commit_group.sync.aligned;" ::: "memory"); }
template <int N> __device__ __forceinline__ void wg_wait() { asm volatile("wgmma.wait_group.sync.aligned %0;" ::"n"(N) : "memory"); }
__device__ __forceinline__ uint32_t desc_lo(uint32_t addr, uint32_t lbo) { return ((addr & 0x3FFFF) >> 4) | ((lbo >> 4) << 16); }
constexpr uint32_t desc_hi(uint32_t sbo, uint32_t swz) { return (sbo >> 4) | (swz << 30); }
constexpr uint32_t HI_SW128 = desc_hi(1024, 1), HI_SW64 = desc_hi(512, 2), HI_SW32 = desc_hi(256, 3), HI_NONE = desc_hi(128, 0);
template <int N> __device__ __forceinline__ void pin(float* d) {
#pragma unroll
  for (int i = 0; i < N; i++) asm volatile("" : "+f"(d[i])::"memory");
}

__device__ __forceinline__ uint32_t lds32(uint32_t a) {
  uint32_t v;
  asm volatile("ld.volatile.shared.u32 %0, [%1];" : "=r"(v) : "r"(a) : "memory");
  return v;
}
__device__ __forceinline__ uint4 ldg128(const void* a) {
  uint4 v;
  asm volatile("ld.global.nc.v4.u32 {%0, %1, %2, %3}, [%4];" : "=r"(v.x), "=r"(v.y), "=r"(v.z), "=r"(v.w) : "l"(a) : "memory");
  return v;
}
__device__ __forceinline__ uint2 ldg64(const void* a) {
  uint2 v;
  asm volatile("ld.global.nc.v2.u32 {%0, %1}, [%2];" : "=r"(v.x), "=r"(v.y) : "l"(a) : "memory");
  return v;
}
__device__ __forceinline__ void ldsm4(uint32_t* r, uint32_t a) {
  asm volatile("ldmatrix.sync.aligned.m8n8.x4.shared.b16 {%0, %1, %2, %3}, [%4];"
               : "=r"(r[0]), "=r"(r[1]), "=r"(r[2]), "=r"(r[3]) : "r"(a) : "memory");
}
__device__ __forceinline__ void ldsm4t(uint32_t* r, uint32_t a) {
  asm volatile("ldmatrix.sync.aligned.m8n8.x4.trans.shared.b16 {%0, %1, %2, %3}, [%4];"
               : "=r"(r[0]), "=r"(r[1]), "=r"(r[2]), "=r"(r[3]) : "r"(a) : "memory");
}
__device__ __forceinline__ uint4 lds128(uint32_t a) {
  uint4 v;
  asm volatile("ld.shared.v4.u32 {%0, %1, %2, %3}, [%4];" : "=r"(v.x), "=r"(v.y), "=r"(v.z), "=r"(v.w) : "r"(a) : "memory");
  return v;
}
__device__ __forceinline__ void sts128(uint32_t a, uint32_t x, uint32_t y, uint32_t z, uint32_t w) {
  asm volatile("st.shared.v4.u32 [%0], {%1, %2, %3, %4};" ::"r"(a), "r"(x), "r"(y), "r"(z), "r"(w) : "memory");
}
__device__ __forceinline__ void stsm4(uint32_t a, const uint32_t* r) {
  asm volatile("stmatrix.sync.aligned.m8n8.x4.shared.b16 [%0], {%1, %2, %3, %4};" ::"r"(a), "r"(r[0]), "r"(r[1]), "r"(r[2]), "r"(r[3]) : "memory");
}
__device__ __forceinline__ void stsm4t(uint32_t a, const uint32_t* r) {
  asm volatile("stmatrix.sync.aligned.m8n8.x4.trans.shared.b16 [%0], {%1, %2, %3, %4};" ::"r"(a), "r"(r[0]), "r"(r[1]), "r"(r[2]), "r"(r[3]) : "memory");
}
__device__ __forceinline__ uint32_t pack2(float lo, float hi) {
  uint32_t r;
  asm("cvt.rn.bf16x2.f32 %0, %1, %2;" : "=r"(r) : "f"(hi), "f"(lo));
  return r;
}
__device__ __forceinline__ uint32_t movm(uint32_t a) {
  uint32_t d;
  asm volatile("movmatrix.sync.aligned.m8n8.trans.b16 %0, %1;" : "=r"(d) : "r"(a));
  return d;
}
__device__ __forceinline__ uint32_t bmul(uint32_t a, uint32_t b) {
  uint32_t d;
  asm("mul.rn.bf16x2 %0, %1, %2;" : "=r"(d) : "r"(a), "r"(b));
  return d;
}
__device__ __forceinline__ uint32_t badd(uint32_t a, uint32_t b) {
  uint32_t d;
  asm("add.rn.bf16x2 %0, %1, %2;" : "=r"(d) : "r"(a), "r"(b));
  return d;
}
__device__ __forceinline__ float bf_lo(uint32_t x) { return __uint_as_float(x << 16); }
__device__ __forceinline__ float bf_hi(uint32_t x) { return __uint_as_float(x & 0xFFFF0000u); }
__device__ __forceinline__ float ex2(float x) {
  float y;
  asm("ex2.approx.ftz.f32 %0, %1;" : "=f"(y) : "f"(x));
  return y;
}
__device__ __forceinline__ float rcp(float x) {
  float y;
  asm("rcp.approx.ftz.f32 %0, %1;" : "=f"(y) : "f"(x));
  return y;
}
__device__ __forceinline__ void mma16816(float* d, uint32_t a0, uint32_t a1, uint32_t a2, uint32_t a3, uint32_t b0, uint32_t b1) {
  asm volatile("mma.sync.aligned.m16n8k16.row.col.f32.bf16.bf16.f32 {%0, %1, %2, %3}, {%4, %5, %6, %7}, {%8, %9}, {%0, %1, %2, %3};"
               : "+f"(d[0]), "+f"(d[1]), "+f"(d[2]), "+f"(d[3])
               : "r"(a0), "r"(a1), "r"(a2), "r"(a3), "r"(b0), "r"(b1));
}
__device__ __forceinline__ void mma1688(float* d, uint32_t a0, uint32_t a1, uint32_t b0) {
  asm volatile("mma.sync.aligned.m16n8k8.row.col.f32.bf16.bf16.f32 {%0, %1, %2, %3}, {%4, %5}, {%6}, {%0, %1, %2, %3};"
               : "+f"(d[0]), "+f"(d[1]), "+f"(d[2]), "+f"(d[3])
               : "r"(a0), "r"(a1), "r"(b0));
}

template <int N> struct WgRS;
template <int N> struct WgSST;
template <> struct WgRS<32> {
  template <uint32_t HB>
  static __device__ __forceinline__ void mma(float* d, const uint32_t* a, uint32_t db) {
    asm volatile("{\n.reg .pred p;\n.reg .b64 db;\nsetp.ne.b32 p, %22, 0;\n"
      "mov.b64 db, {%20, %21};\n"
      "wgmma.mma_async.sync.aligned.m64n32k16.f32.bf16.bf16 {"
      "%0, %1, %2, %3, %4, %5, %6, %7, %8, %9, %10, %11, %12, %13, %14, %15"
      "}, {%16, %17, %18, %19}, db, p, 1, 1, 1;\n}\n"
      : "+f"(d[0]), "+f"(d[1]), "+f"(d[2]), "+f"(d[3]), "+f"(d[4]), "+f"(d[5]), "+f"(d[6]), "+f"(d[7]),
        "+f"(d[8]), "+f"(d[9]), "+f"(d[10]), "+f"(d[11]), "+f"(d[12]), "+f"(d[13]), "+f"(d[14]), "+f"(d[15])
      : "r"(a[0]), "r"(a[1]), "r"(a[2]), "r"(a[3]), "r"(db), "n"(HB), "n"(1));
  }
  template <uint32_t HB>
  static __device__ __forceinline__ void set(float* d, const uint32_t* a, uint32_t db) {
    asm volatile("{\n.reg .pred p;\n.reg .b64 db;\nsetp.ne.b32 p, %22, 0;\n"
      "mov.b64 db, {%20, %21};\n"
      "wgmma.mma_async.sync.aligned.m64n32k16.f32.bf16.bf16 {"
      "%0, %1, %2, %3, %4, %5, %6, %7, %8, %9, %10, %11, %12, %13, %14, %15"
      "}, {%16, %17, %18, %19}, db, p, 1, 1, 1;\n}\n"
      : "=f"(d[0]), "=f"(d[1]), "=f"(d[2]), "=f"(d[3]), "=f"(d[4]), "=f"(d[5]), "=f"(d[6]), "=f"(d[7]),
        "=f"(d[8]), "=f"(d[9]), "=f"(d[10]), "=f"(d[11]), "=f"(d[12]), "=f"(d[13]), "=f"(d[14]), "=f"(d[15])
      : "r"(a[0]), "r"(a[1]), "r"(a[2]), "r"(a[3]), "r"(db), "n"(HB), "n"(0));
  }
};
template <> struct WgRS<64> {
  template <uint32_t HB>
  static __device__ __forceinline__ void mma(float* d, const uint32_t* a, uint32_t db) {
    asm volatile("{\n.reg .pred p;\n.reg .b64 db;\nsetp.ne.b32 p, %38, 0;\n"
      "mov.b64 db, {%36, %37};\n"
      "wgmma.mma_async.sync.aligned.m64n64k16.f32.bf16.bf16 {"
      "%0, %1, %2, %3, %4, %5, %6, %7, %8, %9, %10, %11, %12, %13, %14, %15, "
      "%16, %17, %18, %19, %20, %21, %22, %23, %24, %25, %26, %27, %28, %29, %30, %31"
      "}, {%32, %33, %34, %35}, db, p, 1, 1, 1;\n}\n"
      : "+f"(d[0]), "+f"(d[1]), "+f"(d[2]), "+f"(d[3]), "+f"(d[4]), "+f"(d[5]), "+f"(d[6]), "+f"(d[7]),
        "+f"(d[8]), "+f"(d[9]), "+f"(d[10]), "+f"(d[11]), "+f"(d[12]), "+f"(d[13]), "+f"(d[14]), "+f"(d[15]),
        "+f"(d[16]), "+f"(d[17]), "+f"(d[18]), "+f"(d[19]), "+f"(d[20]), "+f"(d[21]), "+f"(d[22]), "+f"(d[23]),
        "+f"(d[24]), "+f"(d[25]), "+f"(d[26]), "+f"(d[27]), "+f"(d[28]), "+f"(d[29]), "+f"(d[30]), "+f"(d[31])
      : "r"(a[0]), "r"(a[1]), "r"(a[2]), "r"(a[3]), "r"(db), "n"(HB), "n"(1));
  }
  template <uint32_t HB>
  static __device__ __forceinline__ void set(float* d, const uint32_t* a, uint32_t db) {
    asm volatile("{\n.reg .pred p;\n.reg .b64 db;\nsetp.ne.b32 p, %38, 0;\n"
      "mov.b64 db, {%36, %37};\n"
      "wgmma.mma_async.sync.aligned.m64n64k16.f32.bf16.bf16 {"
      "%0, %1, %2, %3, %4, %5, %6, %7, %8, %9, %10, %11, %12, %13, %14, %15, "
      "%16, %17, %18, %19, %20, %21, %22, %23, %24, %25, %26, %27, %28, %29, %30, %31"
      "}, {%32, %33, %34, %35}, db, p, 1, 1, 1;\n}\n"
      : "=f"(d[0]), "=f"(d[1]), "=f"(d[2]), "=f"(d[3]), "=f"(d[4]), "=f"(d[5]), "=f"(d[6]), "=f"(d[7]),
        "=f"(d[8]), "=f"(d[9]), "=f"(d[10]), "=f"(d[11]), "=f"(d[12]), "=f"(d[13]), "=f"(d[14]), "=f"(d[15]),
        "=f"(d[16]), "=f"(d[17]), "=f"(d[18]), "=f"(d[19]), "=f"(d[20]), "=f"(d[21]), "=f"(d[22]), "=f"(d[23]),
        "=f"(d[24]), "=f"(d[25]), "=f"(d[26]), "=f"(d[27]), "=f"(d[28]), "=f"(d[29]), "=f"(d[30]), "=f"(d[31])
      : "r"(a[0]), "r"(a[1]), "r"(a[2]), "r"(a[3]), "r"(db), "n"(HB), "n"(0));
  }
};
template <> struct WgSST<48> {
  template <uint32_t HA, uint32_t HB>
  static __device__ __forceinline__ void mma(float* d, uint32_t da, uint32_t db, int sc) {
    asm volatile("{\n.reg .pred p;\n.reg .b64 da, db;\nsetp.ne.b32 p, %28, 0;\n"
      "mov.b64 da, {%24, %25};\nmov.b64 db, {%26, %27};\n"
      "wgmma.mma_async.sync.aligned.m64n48k16.f32.bf16.bf16 {"
      "%0, %1, %2, %3, %4, %5, %6, %7, %8, %9, %10, %11, %12, %13, %14, %15, "
      "%16, %17, %18, %19, %20, %21, %22, %23"
      "}, da, db, p, 1, 1, 0, 1;\n}\n"
      : "+f"(d[0]), "+f"(d[1]), "+f"(d[2]), "+f"(d[3]), "+f"(d[4]), "+f"(d[5]), "+f"(d[6]), "+f"(d[7]),
        "+f"(d[8]), "+f"(d[9]), "+f"(d[10]), "+f"(d[11]), "+f"(d[12]), "+f"(d[13]), "+f"(d[14]), "+f"(d[15]),
        "+f"(d[16]), "+f"(d[17]), "+f"(d[18]), "+f"(d[19]), "+f"(d[20]), "+f"(d[21]), "+f"(d[22]), "+f"(d[23])
      : "r"(da), "n"(HA), "r"(db), "n"(HB), "r"(sc));
  }
};
template <> struct WgSST<80> {
  template <uint32_t HA, uint32_t HB>
  static __device__ __forceinline__ void mma(float* d, uint32_t da, uint32_t db, int sc) {
    asm volatile("{\n.reg .pred p;\n.reg .b64 da, db;\nsetp.ne.b32 p, %44, 0;\n"
      "mov.b64 da, {%40, %41};\nmov.b64 db, {%42, %43};\n"
      "wgmma.mma_async.sync.aligned.m64n80k16.f32.bf16.bf16 {"
      "%0, %1, %2, %3, %4, %5, %6, %7, %8, %9, %10, %11, %12, %13, %14, %15, "
      "%16, %17, %18, %19, %20, %21, %22, %23, %24, %25, %26, %27, %28, %29, %30, %31, "
      "%32, %33, %34, %35, %36, %37, %38, %39"
      "}, da, db, p, 1, 1, 0, 1;\n}\n"
      : "+f"(d[0]), "+f"(d[1]), "+f"(d[2]), "+f"(d[3]), "+f"(d[4]), "+f"(d[5]), "+f"(d[6]), "+f"(d[7]),
        "+f"(d[8]), "+f"(d[9]), "+f"(d[10]), "+f"(d[11]), "+f"(d[12]), "+f"(d[13]), "+f"(d[14]), "+f"(d[15]),
        "+f"(d[16]), "+f"(d[17]), "+f"(d[18]), "+f"(d[19]), "+f"(d[20]), "+f"(d[21]), "+f"(d[22]), "+f"(d[23]),
        "+f"(d[24]), "+f"(d[25]), "+f"(d[26]), "+f"(d[27]), "+f"(d[28]), "+f"(d[29]), "+f"(d[30]), "+f"(d[31]),
        "+f"(d[32]), "+f"(d[33]), "+f"(d[34]), "+f"(d[35]), "+f"(d[36]), "+f"(d[37]), "+f"(d[38]), "+f"(d[39])
      : "r"(da), "n"(HA), "r"(db), "n"(HB), "r"(sc));
  }
};
template <> struct WgSST<192> {
  template <uint32_t HA, uint32_t HB>
  static __device__ __forceinline__ void mma(float* d, uint32_t da, uint32_t db, int sc) {
    asm volatile("{\n.reg .pred p;\n.reg .b64 da, db;\nsetp.ne.b32 p, %100, 0;\n"
      "mov.b64 da, {%96, %97};\nmov.b64 db, {%98, %99};\n"
      "wgmma.mma_async.sync.aligned.m64n192k16.f32.bf16.bf16 {"
      "%0, %1, %2, %3, %4, %5, %6, %7, %8, %9, %10, %11, %12, %13, %14, %15, "
      "%16, %17, %18, %19, %20, %21, %22, %23, %24, %25, %26, %27, %28, %29, %30, %31, "
      "%32, %33, %34, %35, %36, %37, %38, %39, %40, %41, %42, %43, %44, %45, %46, %47, "
      "%48, %49, %50, %51, %52, %53, %54, %55, %56, %57, %58, %59, %60, %61, %62, %63, "
      "%64, %65, %66, %67, %68, %69, %70, %71, %72, %73, %74, %75, %76, %77, %78, %79, "
      "%80, %81, %82, %83, %84, %85, %86, %87, %88, %89, %90, %91, %92, %93, %94, %95"
      "}, da, db, p, 1, 1, 0, 1;\n}\n"
      : "+f"(d[0]), "+f"(d[1]), "+f"(d[2]), "+f"(d[3]), "+f"(d[4]), "+f"(d[5]), "+f"(d[6]), "+f"(d[7]),
        "+f"(d[8]), "+f"(d[9]), "+f"(d[10]), "+f"(d[11]), "+f"(d[12]), "+f"(d[13]), "+f"(d[14]), "+f"(d[15]),
        "+f"(d[16]), "+f"(d[17]), "+f"(d[18]), "+f"(d[19]), "+f"(d[20]), "+f"(d[21]), "+f"(d[22]), "+f"(d[23]),
        "+f"(d[24]), "+f"(d[25]), "+f"(d[26]), "+f"(d[27]), "+f"(d[28]), "+f"(d[29]), "+f"(d[30]), "+f"(d[31]),
        "+f"(d[32]), "+f"(d[33]), "+f"(d[34]), "+f"(d[35]), "+f"(d[36]), "+f"(d[37]), "+f"(d[38]), "+f"(d[39]),
        "+f"(d[40]), "+f"(d[41]), "+f"(d[42]), "+f"(d[43]), "+f"(d[44]), "+f"(d[45]), "+f"(d[46]), "+f"(d[47]),
        "+f"(d[48]), "+f"(d[49]), "+f"(d[50]), "+f"(d[51]), "+f"(d[52]), "+f"(d[53]), "+f"(d[54]), "+f"(d[55]),
        "+f"(d[56]), "+f"(d[57]), "+f"(d[58]), "+f"(d[59]), "+f"(d[60]), "+f"(d[61]), "+f"(d[62]), "+f"(d[63]),
        "+f"(d[64]), "+f"(d[65]), "+f"(d[66]), "+f"(d[67]), "+f"(d[68]), "+f"(d[69]), "+f"(d[70]), "+f"(d[71]),
        "+f"(d[72]), "+f"(d[73]), "+f"(d[74]), "+f"(d[75]), "+f"(d[76]), "+f"(d[77]), "+f"(d[78]), "+f"(d[79]),
        "+f"(d[80]), "+f"(d[81]), "+f"(d[82]), "+f"(d[83]), "+f"(d[84]), "+f"(d[85]), "+f"(d[86]), "+f"(d[87]),
        "+f"(d[88]), "+f"(d[89]), "+f"(d[90]), "+f"(d[91]), "+f"(d[92]), "+f"(d[93]), "+f"(d[94]), "+f"(d[95])
      : "r"(da), "n"(HA), "r"(db), "n"(HB), "r"(sc));
  }
};

struct FftConst {
  uint32_t f[2][4], fi[4][4];
  float ta[4], tb[4];
};
__device__ __forceinline__ void cis(int m, float scale, float& c, float& s) {
  const float a = (float)m * (-6.283185307179586f * scale);
  c = __cosf(a);
  s = __sinf(a);
}
__device__ __forceinline__ void fft_tables(uint32_t (&v)[12], int tw) {
  const int row = tw >> 2, ch = tw & 3;
#pragma unroll
  for (int i = 0; i < 4; i++) {
    float c[2], s[2], x[2];
#pragma unroll
    for (int e = 0; e < 2; e++) {
      cis((((32 * (8 * ch + 2 * i + e) + 15) * (4 * row - 63) + 2048) & 4095) - 2048, 1.f / 4096, c[e], s[e]);
      float gc, gs;
      cis((((row & 15) * (8 * (ch & 1) + 2 * i + e) + 8) & 15) - 8, 1.f / 16, gc, gs);
      x[e] = (row >> 4) == (ch >> 1) ? gc : (ch >> 1) ? gs : -gs;
    }
    v[i] = pack2(c[0] * 0.125f, c[1] * 0.125f);
    v[4 + i] = pack2(s[0] * 0.125f, s[1] * 0.125f);
    v[8 + i] = pack2(x[0], x[1]);
  }
#pragma unroll
  for (int i = 0; i < 12; i++) asm volatile("" : "+r"(v[i]));
}
__device__ __forceinline__ void fft_tables_store(const uint32_t (&v)[12], uint32_t sb, int tw) {
  const int row = tw >> 2;
  const uint32_t x = ((tw ^ (row >> 1)) & 3) << 4, a = sb + OFF_FT + (16 * (row >> 3) + (row & 7)) * 64 + x;
  sts128(a, v[0], v[1], v[2], v[3]);
  sts128(a + 512, v[4], v[5], v[6], v[7]);
  sts128(sb + OFF_GT + row * 64 + x, v[8], v[9], v[10], v[11]);
}
__device__ __forceinline__ void fft_twiddles(FftConst& k, int w, int lane) {
#pragma unroll
  for (int i = 0; i < 4; i++) {
    float c, s;
    cis((2 * (8 * (i >> 1) + 2 * (lane & 3) + (i & 1)) - 15) * (4 * (8 * w + (lane >> 2)) - 63), 1.f / 4096, c, s);
    k.ta[i] = __fdividef(-s, 1.f + c);
    k.tb[i] = s;
  }
  pin<4>(k.ta);
  pin<4>(k.tb);
}
__device__ __forceinline__ void fft_matrices(FftConst& k, uint32_t sb, int w, int lane) {
  const uint32_t x = (lane >> 1) & 3;
#pragma unroll
  for (int i = 0; i < 2; i++) {
    ldsm4(k.f[i], sb + OFF_FT + (16 * w + (lane & 15)) * 64 + (((2 * i + (lane >> 4)) ^ x) << 4));
    ldsm4t(k.fi[i], sb + OFF_FT + (32 * i + lane) * 64 + ((w ^ x) << 4));
#pragma unroll
    for (int j = 0; j < 4; j++) {
      k.fi[2 + i][j] = (j & 1) ? k.fi[i][j - 1] ^ 0x80008000u : k.fi[i][j + 1];
      asm volatile("" : "+r"(k.fi[2 + i][j]));
    }
  }
}
template <bool INV> __device__ __forceinline__ void rot(float& x, float& y, float a, float b) {
  x = fmaf(INV ? -a : a, y, x);
  y = fmaf(INV ? -b : b, x, y);
  x = fmaf(INV ? -a : a, y, x);
}
__device__ __forceinline__ void twiddle_fwd(uint32_t (&a)[4][4], float* d, const FftConst& k) {
#pragma unroll
  for (int q = 0; q < 4; q++)
#pragma unroll
    for (int j = 0; j < 2; j++) {
      float* x = d + 8 * q + 4 * j;
      rot<false>(x[0], x[2], k.ta[2 * j], k.tb[2 * j]);
      rot<false>(x[1], x[3], k.ta[2 * j + 1], k.tb[2 * j + 1]);
      a[q & 2][2 * j + (q & 1)] = pack2(x[0], x[1]);
      a[(q & 2) + 1][2 * j + (q & 1)] = pack2(x[2], x[3]);
    }
}
__device__ __forceinline__ void g_step(float* d, const uint32_t (&a)[4][4], uint32_t dre, uint32_t dim) {
  WgRS<32>::set<HI_SW64>(d, a[0], dre);
  WgRS<32>::set<HI_SW64>(d + 16, a[2], dre);
  WgRS<32>::mma<HI_SW64>(d, a[1], dim);
  WgRS<32>::mma<HI_SW64>(d + 16, a[3], dim);
  wg_commit();
}

__device__ __forceinline__ void conv_channel(const FftConst& k, uint32_t sb, int c, int wg, int w, int lane) {
  const uint32_t cb = sb + off_ch(c), bars = sb + OFF_BAR;
  const uint32_t du = desc_lo(cb, 1024), dg = desc_lo(sb + OFF_GT, 16), dz = desc_lo(cb + U_BYTES, 16);
  float U[32], H[32];
  uint32_t a[4][4], e[4][4];
  const float dv = __uint_as_float(lds32(sb + OFF_D + 4 * c));
  wg_fence();
  WgRS<64>::set<HI_SW32>(H, k.f[0], du + 256);
  WgRS<64>::mma<HI_SW32>(H, k.f[1], du + 256 + 32);
  wg_commit();
  wg_wait<0>();
  pin<32>(H);
  twiddle_fwd(a, H, k);
  if (ATT_GATE && H_EARLY) mbar_wait(bars + 8 * B_ATTN, 0);
  mbar_wait(bars + 8 * (B_U + (c < 3 ? c : 3)), 0);
  TSM(w == 0 && c < 3, 7 + wg);
  if (TOK_G < 8 && c > 0) mbar_wait(bars + 8 * (B_TOK + c - 1), 0);
  wg_fence();
  WgRS<64>::set<HI_SW32>(U, k.f[0], du);
  WgRS<64>::mma<HI_SW32>(U, k.f[1], du + 32);
  wg_commit();
  g_step(H, a, dg, dg + 64);
  wg_wait<1>();
  pin<32>(U);
  if (TOK_G == 1 && lane == 0) mbar_arrive(bars + 8 * (B_TOK + c));
  twiddle_fwd(e, U, k);
  wg_fence();
  g_step(U, e, dg, dg + 64);
  if (TOK_G == 2 && lane == 0) mbar_arrive(bars + 8 * (B_TOK + c));
  wg_wait<0>();
  pin<32>(U);
  pin<32>(H);
#pragma unroll
  for (int j = 0; j < 2; j++) {
    float pr[4][2], pi[4][2];
#pragma unroll
    for (int x = 0; x < 2; x++) {
      H[4 * j + x] += dv;
#pragma unroll
      for (int m = 0; m < 4; m++) {
#pragma unroll
        for (int q = 0; q <= m; q++) {
          const int ih = 16 * (q >> 1) + 2 * (q & 1) + 4 * j + x, iu = 16 * ((m - q) >> 1) + 2 * ((m - q) & 1) + 4 * j + x;
          pr[m][x] = q ? fmaf(H[ih], U[iu], pr[m][x]) : H[ih] * U[iu];
          pi[m][x] = q ? fmaf(H[ih], U[iu + 8], pi[m][x]) : H[ih] * U[iu + 8];
          pr[m][x] = fmaf(-H[ih + 8], U[iu + 8], pr[m][x]);
          pi[m][x] = fmaf(H[ih + 8], U[iu], pi[m][x]);
        }
      }
    }
#pragma unroll
    for (int m = 0; m < 4; m++) {
      a[m & 2][2 * j + (m & 1)] = pack2(pr[m][0], pr[m][1]);
      a[(m & 2) + 1][2 * j + (m & 1)] = pack2(pi[m][0], pi[m][1]);
    }
  }
  wg_fence();
  g_step(U, a, dg + 64, dg);
  if (TOK_G == 3 && lane == 0) mbar_arrive(bars + 8 * (B_TOK + c));
  const uint32_t za = cb + U_BYTES + (8 * w + (lane & 7)) * 128 + (((lane >> 3) ^ (lane & 7)) << 4);
  const uint32_t ya = cb + (lane >> 4) * 1024 + (8 * w + (lane & 7)) * 32 + ((((lane >> 3) ^ (lane >> 2)) & 1) << 4);
  wg_sync(1 + wg);
  wg_wait<0>();
  pin<32>(U);
  TSIF(w == 0, 80 + c);
#pragma unroll
  for (int p = 0; p < 2; p++) {
#pragma unroll
    for (int i = 0; i < 4; i++) {
      const int j = i & 1;
      float* x = U + 16 * p + 4 * j + (i & 2);
      rot<true>(x[8], x[0], k.ta[2 * j], k.tb[2 * j]);
      rot<true>(x[9], x[1], k.ta[2 * j + 1], k.tb[2 * j + 1]);
      e[p][i] = pack2(x[8], x[9]);
      e[2 + p][i] = pack2(x[0], x[1]);
    }
    stsm4(za ^ (64 * p), e[p]);
    stsm4((za ^ (64 * p)) + 4096, e[2 + p]);
  }
  fence_async_smem();
  wg_sync(1 + wg);
  wg_fence();
  WgRS<64>::set<HI_SW128>(H, k.fi[0], dz);
#pragma unroll
  for (int ks = 1; ks < 4; ks++) WgRS<64>::mma<HI_SW128>(H, k.fi[ks], dz + 128 * ks);
  wg_commit();
  wg_wait<0>();
  pin<32>(H);
  TSIF(w == 0, 88 + c);
#pragma unroll
  for (int j = 0; j < 8; j++)
    a[j >> 2][j & 3] = j < 2 ? pack2(H[4 * j], H[4 * j + 1]) : pack2(H[4 * j] + H[4 * j - 6], H[4 * j + 1] + H[4 * j - 5]);
  stsm4(ya, a[0]);
  stsm4(ya + 2048, a[1]);
  fence_async_smem();
  __syncwarp();
}

__device__ __forceinline__ void prep_slab(uint4* res, const uint2* sw, uint32_t sb, int slab, int w, int lane) {
  const int t = lane & 3, tp = (lane & 7) >> 1, pos = 8 * tp + 2 * (((lane >> 3) + tp) & 3) + (lane & 1);
  const uint32_t base = sb + OFF_KVS + slab * KVS_BYTES + pos * 128;
  uint32_t kk[2][4][4], vv[2][4];
  mbar_wait(sb + OFF_BAR + 8 * (B_KV + slab), 0);
#pragma unroll
  for (int h = 0; h < 2; h++) {
#pragma unroll
    for (int j = 0; j < 4; j++) {
      const uint32_t a = base + 128 * j;
      ldsm4t(kk[h][j], a + (((w + 4 * h) ^ ((a >> 7) & 7)) << 4));
    }
    const uint32_t a = base + KVS_V;
    ldsm4t(vv[h], a + (((w + 4 * h) ^ ((a >> 7) & 7)) << 4));
  }
#pragma unroll
  for (int h = 0; h < 2; h++) {
    uint32_t (&k)[4][4] = kk[h];
    uint32_t (&v)[4] = vv[h];
    const uint32_t w0 = __byte_perm(sw[h].x, 0, 0x1010), w1 = __byte_perm(sw[h].x, 0, 0x3232);
    const uint32_t w2 = __byte_perm(sw[h].y, 0, 0x1010), w3 = __byte_perm(sw[h].y, 0, 0x3232);
#pragma unroll
    for (int m = 0; m < 4; m++)
      v[m] = bmul(badd(badd(badd(bmul(k[0][m], w3), bmul(k[1][m], w2)), bmul(k[2][m], w1)), bmul(k[3][m], w0)), v[m]);
    uint32_t a[4];
#pragma unroll
    for (int m = 0; m < 4; m++) a[m] = (t & 1) ? v[(m + 3) & 3] : v[m];
    res[h] = (t & 2) ? make_uint4(a[2], a[3], a[0], a[1]) : make_uint4(a[0], a[1], a[2], a[3]);
  }
}

__device__ __forceinline__ void prep_gate(const Params& p, int b, int w, int lane) {
  uint2 gw[5], x[4][5];
#pragma unroll
  for (int j = 0; j < 5; j++) gw[j] = ldg64(reinterpret_cast<const uint2*>(p.gate_w) + lane + 32 * j);
#pragma unroll
  for (int i = 0; i < 4; i++)
#pragma unroll
    for (int j = 0; j < 5; j++)
      x[i][j] = ldg64(reinterpret_cast<const uint2*>(p.q) + (16 * b + 4 * w + i) * (DIM / 4) + lane + 32 * j);
  float s[4];
#pragma unroll
  for (int i = 0; i < 4; i++) {
    s[i] = 0.f;
#pragma unroll
    for (int j = 0; j < 5; j++) {
      const uint32_t m0 = bmul(x[i][j].x, gw[j].x), m1 = bmul(x[i][j].y, gw[j].y);
      s[i] += (bf_lo(m0) + bf_hi(m0)) + (bf_lo(m1) + bf_hi(m1));
    }
  }
  const bool h = lane & 16, q = lane & 8;
  const float a = (h ? s[2] : s[0]) + __shfl_xor_sync(0xffffffffu, h ? s[0] : s[2], 16);
  const float c = (h ? s[3] : s[1]) + __shfl_xor_sync(0xffffffffu, h ? s[1] : s[3], 16);
  float z = (q ? c : a) + __shfl_xor_sync(0xffffffffu, q ? a : c, 8);
#pragma unroll
  for (int o = 4; o > 0; o >>= 1) z += __shfl_xor_sync(0xffffffffu, z, o);
  z = bf_lo(pack2(z, 0.f));
  if ((lane & 7) == 0) g_gate[16 * b + 4 * w + (lane >> 3)] = bf_lo(pack2(__fdividef(1.f, 1.f + __expf(-z)), 0.f));
}

__device__ __forceinline__ uint32_t bmax(uint32_t a, uint32_t b) {
  uint32_t d;
  asm("max.bf16x2 %0, %1, %2;" : "=r"(d) : "r"(a), "r"(b));
  return d;
}
__device__ __forceinline__ void softmax_two(const float (&l)[2][2], uint32_t& p0, uint32_t& p1) {
  constexpr float kScale = 0.22360679774997896f, kLog2e = 1.4426950408889634f;
  const uint32_t r0 = pack2(l[0][0], l[1][0]), r1 = pack2(l[0][1], l[1][1]);
  const uint32_t x0 = pack2(bf_lo(r0) * kScale, bf_hi(r0) * kScale), x1 = pack2(bf_lo(r1) * kScale, bf_hi(r1) * kScale);
  uint32_t m = bmax(x0, x1);
  m = bmax(m, __shfl_xor_sync(0xffffffffu, m, 1));
  m = bmax(m, __shfl_xor_sync(0xffffffffu, m, 2));
  const float m0 = bf_lo(m) * kLog2e, m1 = bf_hi(m) * kLog2e;
  p0 = pack2(ex2(bf_lo(x0) * kLog2e - m0), ex2(bf_lo(x1) * kLog2e - m0));
  p1 = pack2(ex2(bf_hi(x0) * kLog2e - m1), ex2(bf_hi(x1) * kLog2e - m1));
}

__device__ __forceinline__ void halo_read(uint32_t (&kpv)[10], uint32_t (&vpv)[10], uint32_t (&tg)[7], const uint4* hp) {
#pragma unroll
  for (int j = 0; j < 7; j++) {
    uint32_t x0, x1, x2;
    asm volatile("ld.relaxed.gpu.global.v4.u32 {%0, %1, %2, %3}, [%4];"
                 : "=r"(x0), "=r"(x1), "=r"(x2), "=r"(tg[j]) : "l"(hp + 32 * j) : "memory");
    if (j < 4) kpv[3 * j] = x0; else vpv[3 * j - 10] = x0;
    if (j < 3) kpv[3 * j + 1] = x1; else vpv[3 * j - 9] = x1;
    if (j < 3) kpv[3 * j + 2] = x2; else if (j < 6) vpv[3 * j - 8] = x2;
  }
}

template <int ROT>
__device__ __forceinline__ void pack_qkv(const float* acc, uint32_t (&qlo)[10], uint32_t (&qhi)[10], uint32_t (&klo)[10],
                                         uint32_t (&khi)[10], uint32_t (&vlo)[10], uint32_t (&vhi)[10]) {
#pragma unroll
  for (int j = 0; j < 10; j++) {
    const int x = (j + ROT) % 10, tq = x < 8 ? x : 16 + x, tk = x < 8 ? 8 + x : 18 + x, tv = x < 8 ? 16 + x : 20 + x;
    khi[j] = pack2(acc[4 * tk + 2], acc[4 * tk + 3]);
    vhi[j] = movm(pack2(acc[4 * tv + 2], acc[4 * tv + 3]));
    qlo[j] = pack2(acc[4 * tq], acc[4 * tq + 1]);
    qhi[j] = pack2(acc[4 * tq + 2], acc[4 * tq + 3]);
    klo[j] = pack2(acc[4 * tk], acc[4 * tk + 1]);
    vlo[j] = pack2(acc[4 * tv], acc[4 * tv + 1]);
    asm volatile("" : "+r"(khi[j]), "+r"(qlo[j]), "+r"(qhi[j]), "+r"(klo[j]), "+r"(vlo[j]));
  }
}

__device__ __forceinline__ void attention(float* acc, uint32_t sb, int b, int par, int w, int lane) {
  const int g = lane >> 2, t = lane & 3;
  uint32_t klo[10], khi[10], vlo[10], vhi[10], qlo[10], qhi[10], kpv[10], vpv[10];
  if (tail_first(b & 7)) pack_qkv<8>(acc, qlo, qhi, klo, khi, vlo, vhi);
  else pack_qkv<0>(acc, qlo, qhi, klo, khi, vlo, vhi);
  uint32_t tag = 0;
  if (w == 0 || w == 3) {
    mbar_wait(sb + OFF_BAR + 8 * B_EPOCH, 0);
    tag = lds32(sb + OFF_EPOCH) + 1;
  }
  const uint32_t xa = sb + OFF_KVX + (par * 3) * 2560 + lane * 16;
  if (w < 3) {
    mbar_wait(sb + OFF_BAR + 8 * B_S3, 0);
    sts128(xa + w * 2560, khi[0], khi[1], khi[2], khi[3]);
    sts128(xa + w * 2560 + 512, khi[4], khi[5], khi[6], khi[7]);
    sts128(xa + w * 2560 + 1024, khi[8], khi[9], vhi[0], vhi[1]);
    sts128(xa + w * 2560 + 1536, vhi[2], vhi[3], vhi[4], vhi[5]);
    sts128(xa + w * 2560 + 2048, vhi[6], vhi[7], vhi[8], vhi[9]);
  } else if (b < NCTA - 8) {
    uint4* ho = g_halo + (b * 2 + par) * 224 + lane;
#pragma unroll
    for (int j = 0; j < 7; j++) {
      const uint32_t x0 = j < 4 ? khi[3 * j] : vhi[3 * j - 10], x1 = j < 3 ? khi[3 * j + 1] : vhi[3 * j - 9];
      const uint32_t x2 = j < 3 ? khi[3 * j + 2] : j < 6 ? vhi[3 * j - 8] : 0u;
      asm volatile("st.relaxed.gpu.global.v4.u32 [%0], {%1, %2, %3, %4};" ::"l"(ho + 32 * j), "r"(x0), "r"(x1), "r"(x2), "r"(tag) : "memory");
    }
  }
  TSIF(par == 0 && w == 1, 64);
  TSIF(par == 0 && w == 3, 76);
#pragma unroll
  for (int j = 0; j < 10; j++) vlo[j] = movm(vlo[j]);
  const bool far0 = 2 * t > g, far1 = 2 * t + 1 > g;
  const uint32_t mfar = (far0 ? 0x0000FFFFu : 0u) | (far1 ? 0xFFFF0000u : 0u);
  float slo[4][2], shi[4][2], lg[2][2];
  uint32_t phi[4], plo[4], qml[4], qmh[4];
#pragma unroll
  for (int h = 0; h < 4; h++) {
    const int f = h == 0 ? 0 : h == 1 ? 3 : h == 2 ? 5 : 8, hf = h < 2 ? 2 : 7;
    const bool mine = (h & 1) ? t >= 2 : t < 2;
    qml[h] = mine ? qlo[hf] : 0u;
    qmh[h] = mine ? qhi[hf] : 0u;
    float a[4] = {0.f, 0.f, 0.f, 0.f}, c[4] = {0.f, 0.f, 0.f, 0.f};
    mma16816(a, qlo[f], qhi[f], qlo[f + 1], qhi[f + 1], klo[f], klo[f + 1]);
    mma16816(c, qlo[f], qhi[f], qlo[f + 1], qhi[f + 1], khi[f], khi[f + 1]);
    mma1688(a, qml[h], qmh[h], klo[hf]);
    mma1688(c, qml[h], qmh[h], khi[hf]);
    slo[h][0] = a[0];
    slo[h][1] = a[1];
    shi[h][0] = lg[h & 1][0] = far0 ? a[2] : c[2];
    shi[h][1] = lg[h & 1][1] = far1 ? a[3] : c[3];
    if (!ATT_MERGE && (h & 1)) softmax_two(lg, phi[h - 1], phi[h]);
  }
  TSIF(par == 0 && w == 1, 65);
  wg_sync(1 + par);
  TSIF(par == 0 && w == 1, 66);
  const bool nohist = (w == 0) && (b < 8);
  const uint4* hp = g_halo + ((b - 8) * 2 + par) * 224 + lane;
  uint32_t tg[7];
  if (w > 0) {
    const uint4 v0 = lds128(xa + (w - 1) * 2560), v1 = lds128(xa + (w - 1) * 2560 + 512), v2 = lds128(xa + (w - 1) * 2560 + 1024);
    const uint4 v3 = lds128(xa + (w - 1) * 2560 + 1536), v4 = lds128(xa + (w - 1) * 2560 + 2048);
    kpv[0] = v0.x; kpv[1] = v0.y; kpv[2] = v0.z; kpv[3] = v0.w; kpv[4] = v1.x; kpv[5] = v1.y; kpv[6] = v1.z; kpv[7] = v1.w;
    kpv[8] = v2.x; kpv[9] = v2.y; vpv[0] = v2.z; vpv[1] = v2.w; vpv[2] = v3.x; vpv[3] = v3.y; vpv[4] = v3.z; vpv[5] = v3.w;
    vpv[6] = v4.x; vpv[7] = v4.y; vpv[8] = v4.z; vpv[9] = v4.w;
  } else if (nohist) {
#pragma unroll
    for (int j = 0; j < 10; j++) kpv[j] = vpv[j] = 0u;
  } else {
    TSIF(par == 0, 77);
    halo_read(kpv, vpv, tg, hp);
  }
  if (w == 0 && !nohist) {
    int spins = 0;
    while (true) {
      bool ok = true;
#pragma unroll
      for (int j = 0; j < 7; j++) ok = ok && tg[j] == tag;
      if (__all_sync(0xffffffffu, ok) || ++spins > SPIN_LIMIT) break;
      halo_read(kpv, vpv, tg, hp);
    }
    TSIF(par == 0, 79);
  }
#pragma unroll
  for (int h = 0; h < 4; h++) {
    const int f = h == 0 ? 0 : h == 1 ? 3 : h == 2 ? 5 : 8, hf = h < 2 ? 2 : 7;
    float a[4] = {0.f, 0.f, 0.f, 0.f};
    mma16816(a, qlo[f], qhi[f], qlo[f + 1], qhi[f + 1], kpv[f], kpv[f + 1]);
    mma1688(a, qml[h], qmh[h], kpv[hf]);
    const float ninf = __int_as_float(0xff800000);
    lg[h & 1][0] = far0 ? (nohist ? ninf : a[0]) : slo[h][0];
    lg[h & 1][1] = far1 ? (nohist ? ninf : a[1]) : slo[h][1];
    if (h & 1) {
      softmax_two(lg, plo[h - 1], plo[h]);
      if (ATT_MERGE) {
        const float lh[2][2] = {{shi[h - 1][0], shi[h - 1][1]}, {shi[h][0], shi[h][1]}};
        softmax_two(lh, phi[h - 1], phi[h]);
      }
    }
  }
  TSIF(par == 0 && w <= 1, 67 + w);
  uint32_t ov[20];
#pragma unroll
  for (int hp = 0; hp < 2; hp++) {
    const int hf = hp ? 7 : 2;
    float sh[4] = {0.f, 0.f, 0.f, 0.f}, i0 = 0.f, i1 = 0.f;
#pragma unroll
    for (int e = 0; e < 2; e++) {
      const int h = 2 * hp + e, f = h == 0 ? 0 : h == 1 ? 3 : h == 2 ? 5 : 8;
      const uint32_t a0 = plo[h] & mfar, a2 = plo[h] & ~mfar, a3 = phi[h] & mfar, c1 = phi[h] & ~mfar;
      float sum[4] = {0.f, 0.f, 0.f, 0.f};
      mma1688(sum, plo[h], phi[h], 0x3F803F80u);
      const float r0 = rcp(sum[0]), r1 = rcp(sum[2]);
#pragma unroll
      for (int j = f; j < f + 2; j++) {
        float o[4] = {0.f, 0.f, 0.f, 0.f};
        mma16816(o, a0, 0u, a2, a3, vpv[j], vlo[j]);
        mma1688(o, 0u, c1, vhi[j]);
        ov[2 * j] = pack2(o[0] * r0, o[1] * r0);
        ov[2 * j + 1] = pack2(o[2] * r1, o[3] * r1);
      }
      const bool mine = e ? g >= 4 : g < 4;
      mma16816(sh, a0, 0u, a2, a3, mine ? vpv[hf] : 0u, mine ? vlo[hf] : 0u);
      mma1688(sh, 0u, c1, mine ? vhi[hf] : 0u);
      if (e == 0 || t >= 2) {
        i0 = r0;
        i1 = r1;
      }
    }
    ov[2 * hf] = pack2(sh[0] * i0, sh[1] * i0);
    ov[2 * hf + 1] = pack2(sh[2] * i1, sh[3] * i1);
  }
  TS(32 + 4 * par + w);
  mbar_wait(sb + OFF_BAR + 8 * B_P1, 0);
  const uint32_t oa = sb + OFF_OA + (lane >> 4) * 2048 + (32 * w + 2 * (lane & 15) + par) * 16;
#pragma unroll
  for (int j = 0; j < 5; j++) stsm4(oa + 4096 * j, ov + 4 * j);
  TSIF(par == 0 && w == 0, 120);
  fence_async_smem();
  TSIF(par == 0 && w == 0, 121);
  __syncwarp();
  if (lane == 0) mbar_arrive(sb + OFF_BAR + 8 * B_ATTN);
  TSIF(par == 0 && w == 0, 122);
}

struct Maps {
  CUtensorMap x, wm, wt, k, v, y, wo, qm, qt, om, ot;
};

__device__ __forceinline__ void load_stage(uint32_t sb, int kb, int b, const Maps& m) {
  const uint32_t st = sb + (kb & 3) * STAGE_BYTES, bar = sb + OFF_BAR + 8 * (B_FULL1 + (kb & 3));
  const int r = b >> 3, hg = b & 7, slab = kb - KV_KB;
  const bool kv = slab >= 0 && slab < 5;
  const uint32_t kbar = sb + OFF_BAR + 8 * (B_KV + slab), dst = sb + OFF_KVS + slab * KVS_BYTES;
  mbar_expect_tx(bar, STAGE_BYTES);
  if (kv) mbar_expect_tx(kbar, KVS_BYTES);
  tma_3d(st, &m.x, 64 * kb, 64 * r, 0, bar);
  if (kv && KV_MIX) tma_3d(dst, &m.k, 0, 32 * (b >> 1) - 3, 2 * slab + (b & 1), kbar);
  tma_3d(st + ST_W, &m.wm, 80 * hg + (tail_first(hg) ? 16 : 0), 64 * kb, 0, bar);
  if (kv && KV_MIX) tma_3d(dst + KVS_V, &m.v, 0, 32 * (b >> 1), 2 * slab + (b & 1), kbar);
  tma_3d(st + ST_WT, &m.wt, 80 * hg + (tail_first(hg) ? 0 : 64), 64 * kb, 0, bar);
  if (kv && !KV_MIX) tma_3d(dst, &m.k, 0, 32 * (b >> 1) - 3, 2 * slab + (b & 1), kbar);
  if (kv && !KV_MIX) tma_3d(dst + KVS_V, &m.v, 0, 32 * (b >> 1), 2 * slab + (b & 1), kbar);
}

__global__ void __launch_bounds__(NTHR, 1) fused_kernel(const __grid_constant__ Maps m, const Params p) {
  extern __shared__ __align__(1024) uint8_t smem[];
  const uint32_t sb = (uint32_t)__cvta_generic_to_shared(smem);
  const uint32_t bars = sb + OFF_BAR;
  const int tid = threadIdx.x, lane = tid & 31;
  int b = blockIdx.x;
  if (BMAP == 1) b = (((b & 63) >> 3) * 2 + (b & 1)) * 8 + (((b < 64 ? 0x6521 : 0x7430) >> (4 * ((b >> 1) & 3))) & 7);
  if (BMAP == 2) b = ((b & 63) >> 2) * 8 + (((b < 64 ? 0x6521 : 0x7430) >> (4 * (b & 3))) & 7);
  if (BMAP == 3) b = (((b & 63) >> 3) * 2 + (b & 1)) * 8 + (((b < 64 ? 0x7430 : 0x6521) >> (4 * ((b >> 1) & 3))) & 7);
  if (BMAP == 4) b = (((b >> 4) * 2 + (b & 1)) * 8) + ((b >> 1) & 7);
  if (BMAP == 5) b = 127 - b;
  const int r = b >> 3, hg = b & 7;

  if (tid == T_ISSUE) {
    TSM(true, 0);
#pragma unroll
    for (int i = 0; i < 4; i++) mbar_init(bars + 8 * (B_FULL1 + i), 1);
#pragma unroll
    for (int i = 0; i < 3; i++) mbar_init(bars + 8 * (B_KV + i), 1);
    fence_async_smem();
#pragma unroll 1
    for (int kb = 0; kb <= PRE2; kb++) load_stage(sb, kb, b, m);
  } else if (tid >= T_PF && tid < T_PF + 11) {
    tm_prefetch(&m.x + (tid - T_PF));
  } else if (tid == T_INIT) {
#pragma unroll
    for (int i = 0; i < 4; i++) mbar_init(bars + 8 * (B_EMPTY1 + i), 8);
#pragma unroll
    for (int i = 0; i < 8; i++) mbar_init(bars + 8 * (B_FULL2 + i), 1);
#pragma unroll
    for (int i = 0; i < 4; i++) mbar_init(bars + 8 * (B_EMPTY2 + i), 8);
#pragma unroll
    for (int i = 0; i < 4; i++) mbar_init(bars + 8 * (B_U + i), 1);
    mbar_init(bars + 8 * B_HA, 4);
    mbar_init(bars + 8 * B_GATE, 4);
    mbar_init(bars + 8 * B_HB, 1);
    mbar_init(bars + 8 * B_KVD, 4);
    mbar_init(bars + 8 * B_QF, 1);
    mbar_init(bars + 8 * B_ATTN, 8);
    mbar_init(bars + 8 * B_P1, 8);
    mbar_init(bars + 8 * B_C34, 1);
#pragma unroll
    for (int i = 0; i < 5; i++) mbar_init(bars + 8 * (B_YST + i), 4);
#pragma unroll
    for (int i = 0; i < 5; i++) mbar_init(bars + 8 * (B_TOK + i), 4);
    mbar_init(bars + 8 * B_YSIG, 1);
    mbar_init(bars + 8 * B_YFULL, 1);
    mbar_init(bars + 8 * B_EPOCH, 1);
    mbar_init(bars + 8 * B_PREP, 4);
    mbar_init(bars + 8 * B_USIG, 1);
    mbar_init(bars + 8 * B_WST, 1);
#pragma unroll
    for (int i = 3; i < 5; i++) mbar_init(bars + 8 * (B_KV + i), 1);
    mbar_init(bars + 8 * B_E3, 8);
    mbar_init(bars + 8 * B_LAST, 1);
    mbar_init(bars + 8 * B_OSIG, 1);
    mbar_init(bars + 8 * B_WOP, 1);
    fence_async_smem();
  }
  const int warp = __shfl_sync(0xffffffffu, tid >> 5, 0), wg = warp >> 2, w = warp & 3;
  __syncthreads();

  if (wg == 3) {
    asm volatile("setmaxnreg.dec.sync.aligned.u32 56;");
    if (w == 0) {
      if (lane == 0) {
#pragma unroll 1
        for (int kb = 1 + PRE2; kb < 10; kb++) {
          if (kb >= 4) mbar_wait(bars + 8 * (kb == 7 ? B_E3 : B_EMPTY1 + (kb & 3)), (kb >> 3) & 1);
          TSIF(kb >= 4, 44 + kb);
          if (WO_EARLY && kb == KV_KB + 4) mbar_wait(bars + 8 * B_WOP, 0);
          load_stage(sb, kb, b, m);
          if (kb == TRIG_KB) mbar_arrive(bars + 8 * B_LAST);
          if (WO_EARLY && kb == WO_EARLY) {
            mbar_expect_tx(bars + 8 * B_WST, WO_BYTES / 2);
            tma_3d(sb + OFF_WS, &m.wo, 0, 40 * r, 5 * hg, bars + 8 * B_WST);
          }
        }
        mbar_wait(bars + 8 * (WO_EARLY ? WL_TRIG : B_WOP), 0);
        mbar_wait(bars + 8 * B_EPOCH, 0);
        flag_wait(g_cnt + C_W + 32 * hg, (lds32(sb + OFF_EPOCH) + 1) * 16);
        TS(30);
#pragma unroll 1
        for (int j = 0; j < 8; j++) {
          if (j >= 6) mbar_wait(bars + 8 * (B_EMPTY2 + j - 6), 0);
          if (WO_EARLY && j == 4) mbar_wait(bars + 8 * B_ATTN, 0);
          TSIF(j >= 6, 100 + j);
          if (RF_GATE && j == 6) mbar_wait(bars + 8 * B_YSIG, 0);
          mbar_expect_tx(bars + 8 * (B_FULL2 + j), j == 0 ? WO_BYTES : j == 5 ? O_BYTES + WO_BYTES + 512 : O_BYTES + WO_BYTES);
          bulk_load(sb + off_w(j), g_WO + (hg * 8 + step_src(hg, j)) * 800, WO_BYTES, bars + 8 * (B_FULL2 + j));
        }
        mbar_wait(bars + 8 * (B_EMPTY2 + 3), 0);
        mbar_expect_tx(bars + 8 * B_QF, O_BYTES);
        tma_2d(sb + OFF_QS, &m.qm, 80 * hg, 128 * r, bars + 8 * B_QF);
        tma_2d(sb + OFF_QT, &m.qt, 80 * hg + 64, 128 * r, bars + 8 * B_QF);
      }
    } else if (w == 1) {
      unsigned epoch = 0;
      if (lane == 0) {
        epoch = atomicAdd(g_cnt + C_LAUNCH, 1u) / NCTA;
        asm volatile("st.shared.u32 [%0], %1;" ::"r"(sb + OFF_EPOCH), "r"(epoch) : "memory");
        mbar_arrive(bars + 8 * B_EPOCH);
        mbar_wait(bars + 8 * B_KVD, 0);
        mbar_expect_tx(bars + 8 * B_HB, 5 * 4096);
#pragma unroll 1
        for (int c = 0; c < 5; c++) {
          if (c == 3) mbar_wait(bars + 8 * B_S3, 0);
          bulk_load(sb + off_ch(c) + U_BYTES, p.ssm_k + (5 * b + c) * SEQ, 4096, bars + 8 * B_HB);
        }
#pragma unroll
        for (int c = 0; c < 4; c++) mbar_expect_tx(bars + 8 * (B_U + c), c < 3 ? U_BYTES : 2 * U_BYTES);
        const uint4* usrc = g_U + 5 * b * U_PITCH;
        mbar_wait(bars + 8 * B_USIG, 0);
        flag_wait(g_cnt + C_PREP + 32 * (b & 15), (epoch + 1) * NCTA);
        TS(23);
#pragma unroll
        for (int c = 0; c < 5; c++) {
          if (c == 3) mbar_wait(bars + 8 * (B_U + 2), 0);
          bulk_load(sb + off_ch(c), usrc + c * U_PITCH, U_BYTES, bars + 8 * (B_U + (c < 3 ? c : 3)));
          TSIF(c == 0 || c == 4, 116 + (c >> 2));
        }
      }
      epoch = __shfl_sync(0xffffffffu, epoch, 0);
      if (lane < 8) {
        const int src = (b & ~7) | step_src(hg, lane);
        mbar_wait(bars + 8 * B_OSIG, 0);
        flag_wait(g_cnt + C_O + 32 * src, epoch + 1);
        if (lane >= 1 && lane < 4) bulk_load(sb + off_o(lane), g_O + src * 1280, O_BYTES, bars + 8 * (B_FULL2 + lane));
        __syncwarp(0xff);
        TS(21);
        if (lane == 5) bulk_load(sb + OFF_GATE, g_gate + 128 * r, 512, bars + 8 * (B_FULL2 + 5));
#pragma unroll 1
        for (int j = 4; j < 8; j++) {
          if (lane == j) {
            mbar_wait(bars + 8 * (j < 6 ? B_C34 : B_EMPTY2 + j - 6), 0);
            if (RF_GATE && j == 6) mbar_wait(bars + 8 * B_YSIG, 0);
            bulk_load(sb + off_o(j), g_O + src * 1280, O_BYTES, bars + 8 * (B_FULL2 + j));
          }
          __syncwarp(0xff);
        }
        TS(22);
      }
    } else if (w == 2) {
      mbar_wait(bars + 8 * B_PREP, 0);
      flag_signal(g_cnt + C_PREP, 16, lane);
      TS(25);
      if (lane == 0) mbar_arrive(bars + 8 * B_USIG);
      mbar_wait(bars + 8 * B_GATE, 0);
      if ((NOMB & 1) && lane == 0) asm volatile("fence.release.gpu;" ::: "memory");
      mbar_wait(bars + 8 * B_ATTN, 0);
      if (lane == 0) {
        if (O_DEFER) mbar_wait(bars + 8 * (B_U + 3), 0);
        asm volatile("cp.async.bulk.global.shared::cta.bulk_group [%0], [%1], 20480;\ncp.async.bulk.commit_group;\n"
                     "cp.async.bulk.wait_group 0;\nfence.proxy.async.global;" ::"l"(g_O + b * 1280), "r"(sb + OFF_OA) : "memory");
      }
      if (!(NOMB & 1)) flag_signal(g_cnt + C_O + 32 * b, 1, lane);
      else if (lane == 0) flag_bump(g_cnt + C_O + 32 * b);
      TS(26);
      if (lane == 0) mbar_arrive(bars + 8 * B_OSIG);
      if (!(NOMB & 4)) {
        mbar_wait(bars + 8 * B_WOP, 0);
        flag_signal(g_cnt + C_W + 32 * hg, 1, lane);
      }
      TS(73);
    } else {
      if (lane == 0) {
        if (!WO_EARLY) {
          mbar_wait(bars + 8 * WB_TRIG, 0);
          mbar_expect_tx(bars + 8 * B_WST, WO_BYTES / 2);
          tma_3d(sb + OFF_WS, &m.wo, 0, 40 * r, 5 * hg, bars + 8 * B_WST);
        }
        mbar_wait(bars + 8 * B_WST, 0);
        if (!WO_EARLY) mbar_wait(bars + 8 * WO_TRIG, 0);
        uint4* dst = g_WO + (hg * 8 + (r >> 1)) * 800 + (r & 1) * 80;
#pragma unroll 1
        for (int n = 0; n < 5; n++)
          asm volatile("cp.async.bulk.global.shared::cta.bulk_group [%0], [%1], 1280;" ::"l"(dst + 160 * n), "r"(sb + OFF_WS + 1280 * n) : "memory");
        asm volatile("cp.async.bulk.commit_group;\ncp.async.bulk.wait_group 0;\nfence.proxy.async.global;" ::: "memory");
        if (NOMB & 4) flag_bump(g_cnt + C_W + 32 * hg);
        mbar_arrive(bars + 8 * B_WOP);
      }
      TS(71);
      if (lane == 0) {
#pragma unroll 1
        for (int c = 0; c < 5; c++) {
          mbar_wait(bars + 8 * (B_YST + c), 0);
          asm volatile("cp.async.bulk.global.shared::cta.bulk_group [%0], [%1], 4096;\ncp.async.bulk.commit_group;"
                       ::"l"(g_Y + (5 * b + c) * Y_PITCH), "r"(sb + off_ch(c)) : "memory");
          if (c == 2) {
            asm volatile("cp.async.bulk.wait_group.read 0;" ::: "memory");
            mbar_arrive(bars + 8 * B_C34);
          }
        }
        asm volatile("cp.async.bulk.wait_group 0;\nfence.proxy.async.global;" ::: "memory");
        if (!(NOMB & 2)) asm volatile("fence.release.gpu;" ::: "memory");
        flag_bump(g_cnt + C_Y + 32 * (b >> 4));
        TS(27);
        mbar_arrive(bars + 8 * B_YSIG);
        mbar_expect_tx(bars + 8 * B_YFULL, 20480);
        flag_wait(g_cnt + C_Y + 32 * hg, (lds32(sb + OFF_EPOCH) + 1) * 16);
        TS(24);
        tma_2d(sb + OFF_YT, &m.y, 128 * r, 80 * hg, bars + 8 * B_YFULL);
        tma_2d(sb + OFF_YT + 10240, &m.y, 128 * r + 64, 80 * hg, bars + 8 * B_YFULL);
      }
    }
  } else {
    asm volatile("setmaxnreg.inc.sync.aligned.u32 152;");
    if (wg < 2) {
      float acc[120];
#pragma unroll
      for (int i = 0; i < 120; i++) acc[i] = 0.f;
      const uint32_t da = desc_lo(sb + wg * 8192, 16), db = desc_lo(sb + ST_W, 8192), dc = desc_lo(sb + ST_WT, 2048);
      if (PW1) pin<120>(acc);
      if (PW1 == 2) mbar_wait(bars + 8 * B_FULL1, 0);
#pragma unroll 1
      for (int kb = 0; kb < 10; kb++) {
        mbar_wait(bars + 8 * (B_FULL1 + (kb & 3)), (kb >> 2) & 1);
        const uint32_t so = (kb & 3) * (STAGE_BYTES >> 4);
        wg_fence();
#pragma unroll
        for (int k = 0; k < 4; k++) {
          WgSST<192>::mma<HI_SW128, HI_SW128>(acc, da + so + 2 * k, db + so + 128 * k, 1);
          WgSST<48>::mma<HI_SW128, HI_SW32>(acc + 96, da + so + 2 * k, dc + so + 32 * k, 1);
        }
        wg_commit();
        wg_wait<1>();
        if (kb > 0 && lane == 0) mbar_arrive(bars + 8 * (kb == 4 ? B_E3 : B_EMPTY1 + ((kb - 1) & 3)));
      }
      wg_wait<0>();
      pin<120>(acc);
      if (lane == 0) mbar_arrive(bars + 8 * B_P1);
      TSM(w == 0, 3 + wg);
      attention(acc, sb, b, wg, w, lane);
    } else {
      const int tw = tid & 127, chl = 64 * (b & 1) + 8 * w + (lane >> 2);
      uint4* up = g_U + chl * U_PITCH + ((4 * (b >> 1) + (lane & 3)) ^ ((b >> 2) & 1));
      uint2 sw[10];
      uint32_t dv = 0;
      if (lane < 5) dv = __ldg(reinterpret_cast<const unsigned short*>(p.ssm_D) + 5 * b + lane);
#pragma unroll
      for (int i = 0; i < 10; i++) sw[i] = ldg64(reinterpret_cast<const uint2*>(p.shift_k) + chl + 128 * (i >> 1) + 32 * (i & 1));
      uint32_t tab[12];
      fft_tables(tab, tw);
      uint4 res[10];
#pragma unroll
      for (int i = 0; i < 10; i++) res[i] = make_uint4(0, 0, 0, 0);
#pragma unroll 1
      for (int slab = 0; slab < 5; slab++) {
#pragma unroll
        for (int i = 0; i < 8; i++) res[i] = res[i + 2];
        prep_slab(res + 8, sw, sb, slab, w, lane);
        TSIF(w == 0, 99 + 4 * slab);
#pragma unroll
        for (int i = 0; i < 8; i++) sw[i] = sw[i + 2];
      }
      TSIF(w == 0, 28);
      __syncwarp();
      if (lane == 0) mbar_arrive(bars + 8 * B_KVD + ((res[8].x ^ res[9].x) & p.zero));
      mbar_wait(bars + 8 * B_KVD, 0);
      fft_tables_store(tab, sb, tw);
      mbar_wait(bars + 8 * B_LAST, 0);
#pragma unroll
      for (int i = 0; i < 10; i++) up[(128 * (i >> 1) + 32 * (i & 1)) * U_PITCH] = res[i];
      __syncwarp();
      if (lane == 0) mbar_arrive(bars + 8 * B_PREP);
      TSIF(w == 0, 5);
      mbar_wait(bars + 8 * (G_AFTER ? B_USIG : B_LAST), 0);
      prep_gate(p, b, w, lane);
      __syncwarp();
      if (lane == 0) mbar_arrive(bars + 8 * B_GATE);
      TSIF(w == 0, 72);
      mbar_wait(bars + 8 * B_HB, 0);
      TSIF(w == 0, 123);
      const uint32_t ha = sb + U_BYTES + ((tw >> 3) * 16 + 8 + (tw & 7)) * 16;
      uint4 hv[5];
#pragma unroll
      for (int c = 0; c < 5; c++) hv[c] = lds128(ha + off_ch(c));
      __syncwarp();
#pragma unroll
      for (int c = 0; c < 5; c++) sts128((ha ^ 16) + off_ch(c), hv[c].x, hv[c].y, hv[c].z, hv[c].w);
      if (tw < 5) asm volatile("st.shared.f32 [%0], %1;" ::"r"(sb + OFF_D + 4 * tw), "f"(bf_lo(dv) * 0.125f) : "memory");
      fence_async_smem();
      __syncwarp();
      if (lane == 0) mbar_arrive(bars + 8 * B_HA);
      TSIF(w == 0, 6);
    }

    FftConst fc;
    fft_twiddles(fc, w, lane);
    mbar_wait(bars + 8 * B_HA, 0);
    fft_matrices(fc, sb, w, lane);
    if (ATT_GATE && !H_EARLY) mbar_wait(bars + 8 * B_ATTN, 0);
    TSIF(w == 0 && wg == 2, 124);
#pragma unroll 1
    for (int c = wg == 2 ? 0 : wg + 1; c < 5; c += 3) {
      conv_channel(fc, sb, c, wg, w, lane);
      if (lane == 0) mbar_arrive(bars + 8 * (B_YST + c));
      TSM(w == 0, 10 + c);
    }

    if (wg < 2) {
      const int g = lane >> 2;
      float acc[40];
#pragma unroll
      for (int i = 0; i < 40; i++) acc[i] = 0.f;
      const uint32_t da = desc_lo(sb + wg * 1024, 2048), db = desc_lo(sb, 2560);
      mbar_wait(bars + 8 * B_ATTN, 0);
      mbar_wait(bars + 8 * (B_YST + 3), 0);
      mbar_wait(bars + 8 * (B_YST + 4), 0);
      if (PW2) mbar_wait(bars + 8 * B_FULL2, 0);
#pragma unroll 1
      for (int j = 0; j < 8; j++) {
        mbar_wait(bars + 8 * (B_FULL2 + j), 0);
        const uint32_t oa = da + (off_o(j) >> 4), ob = db + (off_w(j) >> 4);
        wg_fence();
#pragma unroll
        for (int k = 0; k < 5; k++) WgSST<80>::mma<HI_NONE, HI_SW32>(acc, oa + 256 * k, ob + 32 * k, 1);
        wg_commit();
        wg_wait<1>();
        if (j >= 1 && j <= 4 && lane == 0) mbar_arrive(bars + 8 * (B_EMPTY2 + j - 1));
      }
      TSIF(w == 0 && wg == 0, 113);
      const int tr = 64 * wg + 16 * w + (lane & 15);
      const uint32_t fm = sb + OFF_QS + tr * 128, fx = (lane >> 4) ^ (tr & 7);
      const uint32_t ft = sb + OFF_QT + tr * 32 + (((lane >> 4) ^ (tr >> 2)) & 1) * 16;
      const float g0 = __uint_as_float(lds32(sb + OFF_GATE + (64 * wg + 16 * w + g) * 4));
      const float g1 = __uint_as_float(lds32(sb + OFF_GATE + (64 * wg + 16 * w + 8 + g) * 4));
      const uint32_t ga = pack2(g0, g0), gb = pack2(g1, g1);
      const uint32_t na = pack2(1.f - g0, 1.f - g0), nb = pack2(1.f - g1, 1.f - g1);

      wg_wait<0>();
      pin<40>(acc);
      TSM(w == 0, 17 + wg);
      uint32_t pb[20];
#pragma unroll
      for (int j = 0; j < 10; j++) {
        pb[2 * j] = bmul(na, pack2(acc[4 * j], acc[4 * j + 1]));
        pb[2 * j + 1] = bmul(nb, pack2(acc[4 * j + 2], acc[4 * j + 3]));
        asm volatile("" : "+r"(pb[2 * j]), "+r"(pb[2 * j + 1]));
      }
      const uint32_t ya = sb + OFF_YT + wg * 10240 + ((lane >> 4) * 8 + (lane & 7)) * 128 +
                          (((2 * w + (((lane >> 3) & 1) ^ wg)) ^ (lane & 7)) << 4);
      uint32_t qf[20];
      mbar_wait(bars + 8 * B_QF, 0);
#pragma unroll
      for (int j = 0; j < 5; j++) ldsm4(qf + 4 * j, j < 4 ? fm + ((fx ^ (2 * j)) << 4) : ft);
      mbar_wait(bars + 8 * B_YFULL, 0);
      TSIF(w == 0 && wg == 0, 19);
#pragma unroll
      for (int j = 0; j < 5; j++) {
        uint32_t y[4];
        ldsm4t(y, ya + 2048 * j);
#pragma unroll
        for (int i = 0; i < 4; i++) qf[4 * j + i] = badd(bmul((i & 1) ? gb : ga, bmul(qf[4 * j + i], y[i])), pb[4 * j + i]);
      }
#pragma unroll
      for (int j = 0; j < 5; j++) stsm4(j < 4 ? fm + ((fx ^ (2 * j)) << 4) : ft, qf + 4 * j);
      fence_async_smem();
      __syncwarp();
      if (lane == 0) {
        const int row = 64 * wg + 16 * w;
        asm volatile("cp.async.bulk.tensor.2d.global.shared::cta.bulk_group [%0, {%2, %3}], [%1];"
                     ::"l"(&m.om), "r"(sb + OFF_QS + row * 128), "r"(80 * hg), "r"(128 * r + row) : "memory");
        asm volatile("cp.async.bulk.tensor.2d.global.shared::cta.bulk_group [%0, {%2, %3}], [%1];"
                     ::"l"(&m.ot), "r"(sb + OFF_QT + row * 32), "r"(80 * hg + 64), "r"(128 * r + row) : "memory");
        asm volatile("cp.async.bulk.commit_group;\ncp.async.bulk.wait_group.read 0;" ::: "memory");
      }
      TSM(true, 40 + 4 * wg + w);
      if (ENDBAR) asm volatile("bar.sync 15, 256;" ::: "memory");
    }
  }
}

typedef CUresult (*EncodeFn)(CUtensorMap*, CUtensorMapDataType, cuuint32_t, void*, const cuuint64_t*, const cuuint64_t*,
                             const cuuint32_t*, const cuuint32_t*, CUtensorMapInterleave, CUtensorMapSwizzle,
                             CUtensorMapL2promotion, CUtensorMapFloatOOBfill);

void encode(EncodeFn fn, CUtensorMap* tm, const void* base, int rank, const cuuint64_t* dims, const cuuint64_t* strides,
            const cuuint32_t* box, CUtensorMapSwizzle swz) {
  const cuuint32_t ones[3] = {1, 1, 1};
  fn(tm, CU_TENSOR_MAP_DATA_TYPE_BFLOAT16, rank, const_cast<void*>(base), dims, strides, box, ones,
     CU_TENSOR_MAP_INTERLEAVE_NONE, swz, CU_TENSOR_MAP_L2_PROMOTION_L2_128B, CU_TENSOR_MAP_FLOAT_OOB_FILL_NONE);
}

}

extern "C" void kernel_launch(void* const* d_in, const int* in_sizes, int n_in, void* d_out, int out_size) {
  (void)in_sizes; (void)n_in; (void)out_size;
  Params p;
  p.q = (const __nv_bfloat16*)d_in[0];
  p.k = (const __nv_bfloat16*)d_in[1];
  p.v = (const __nv_bfloat16*)d_in[2];
  p.shift_k = (const __nv_bfloat16*)d_in[3];
  p.ssm_k = (const __nv_bfloat16*)d_in[4];
  p.ssm_D = (const __nv_bfloat16*)d_in[5];
  p.wqkv = (const __nv_bfloat16*)d_in[7];
  p.wo = (const __nv_bfloat16*)d_in[8];
  p.gate_w = (const __nv_bfloat16*)d_in[9];
  p.out = (__nv_bfloat16*)d_out;
  p.zero = 0;

  static EncodeFn fn = nullptr;
  static void* yaddr = nullptr;
  if (!fn) {
    cudaDriverEntryPointQueryResult qr;
    void* f = nullptr;
    cudaGetDriverEntryPoint("cuTensorMapEncodeTiled", &f, cudaEnableDefault, &qr);
    fn = (EncodeFn)f;
    cudaGetSymbolAddress(&yaddr, g_Y);
    cudaFuncSetAttribute(fused_kernel, cudaFuncAttributeMaxDynamicSharedMemorySize, SMEM_BYTES);
  }
  Maps m;
  {
    const cuuint64_t dims[3] = {640, 1024, 2}, st[2] = {2560, 1280};
    const cuuint32_t box[3] = {64, 64, 2};
    encode(fn, &m.x, p.q, 3, dims, st, box, CU_TENSOR_MAP_SWIZZLE_128B);
  }
  {
    const cuuint64_t dims[3] = {640, 640, 3}, st[2] = {3840, 1280};
    const cuuint32_t box[3] = {64, 64, 3}, boxt[3] = {16, 64, 3};
    encode(fn, &m.wm, p.wqkv, 3, dims, st, box, CU_TENSOR_MAP_SWIZZLE_128B);
    encode(fn, &m.wt, p.wqkv, 3, dims, st, boxt, CU_TENSOR_MAP_SWIZZLE_32B);
  }
  {
    const cuuint64_t dims[3] = {64, 2048, 10}, st[2] = {1280, 128};
    const cuuint32_t boxk[3] = {64, 35, 1}, boxv[3] = {64, 32, 1};
    encode(fn, &m.k, p.k, 3, dims, st, boxk, CU_TENSOR_MAP_SWIZZLE_128B);
    encode(fn, &m.v, p.v, 3, dims, st, boxv, CU_TENSOR_MAP_SWIZZLE_128B);
  }
  {
    const cuuint64_t dims[3] = {16, 640, 40}, st[2] = {1280, 32};
    const cuuint32_t box[3] = {16, 40, 5};
    encode(fn, &m.wo, p.wo, 3, dims, st, box, CU_TENSOR_MAP_SWIZZLE_32B);
  }
  {
    const cuuint64_t dims[2] = {2048, 640}, st[1] = {Y_PITCH * 16};
    const cuuint32_t box[2] = {64, 80};
    encode(fn, &m.y, yaddr, 2, dims, st, box, CU_TENSOR_MAP_SWIZZLE_128B);
  }
  {
    const cuuint64_t dims[2] = {640, 2048}, st[1] = {1280};
    const cuuint32_t bqm[2] = {64, 128}, bqt[2] = {16, 128}, bom[2] = {64, 16}, bot[2] = {16, 16};
    encode(fn, &m.qm, p.q, 2, dims, st, bqm, CU_TENSOR_MAP_SWIZZLE_128B);
    encode(fn, &m.qt, p.q, 2, dims, st, bqt, CU_TENSOR_MAP_SWIZZLE_32B);
    encode(fn, &m.om, p.out, 2, dims, st, bom, CU_TENSOR_MAP_SWIZZLE_128B);
    encode(fn, &m.ot, p.out, 2, dims, st, bot, CU_TENSOR_MAP_SWIZZLE_32B);
  }
  fused_kernel<<<NCTA, NTHR, SMEM_BYTES>>>(m, p);
}
```

```cpp
#include <cuda.h>
#include <cuda_bf16.h>
#include <cuda_runtime.h>
#include <stdint.h>

namespace {

constexpr int SEQ = 2048, DIM = 640, NCTA = 128, NTHR = 512;

#define TRIG_KB 9
#define KV_KB 2
#define DEV_EXIT 0
#define ATT_GATE 1
#define G_AFTER 0
#define FENCE_LO 0
#define FENCE_HI 0
#define PW1 2
#define PW2 1
#define ENDBAR 0
#define PAD_KB 0
#define Y_ALIAS 1
#define H_EARLY 1
#define NOMB 7
#define WO_EARLY 0
#define SRC_ROT 0
#define WAIT_NS 0
#define WB_TRIG B_LAST
#define G_POS 0
#define TAILF 1
#define T_ISSUE 384
#define T_PF 416
#define T_INIT 448
#define ATT_MERGE 0
#define BMAP 1
#define PRE2 1
#define KV_MIX 0
#define O_DEFER 0
#define TOK_G 1
#define RF_GATE 0
#define WO_TRIG B_WST
#define WL_TRIG B_P1
#define WO_GATE 1

constexpr uint32_t STAGE_BYTES = 47104, ST_W = 16384, ST_WT = 40960;
constexpr uint32_t O_BYTES = 20480, WO_BYTES = 12800;
constexpr uint32_t OFF_OA = 0;
constexpr uint32_t OFF_QS = 3 * O_BYTES, OFF_QT = OFF_QS + 16384;
constexpr uint32_t OFF_WC = 81920;
constexpr uint32_t OFF_WA = 94720;
constexpr uint32_t OFF_GATE = 145920;
constexpr uint32_t OFF_KVX = 147968;
constexpr uint32_t OFF_D = OFF_GATE + 512;
constexpr uint32_t OFF_CH3 = 163840;
constexpr uint32_t CH_BYTES = 12288, U_BYTES = 4096;
constexpr uint32_t OFF_FT = 225280, OFF_GT = 229376;
constexpr uint32_t OFF_CH0 = 188416;
constexpr uint32_t OFF_KVS = OFF_CH0, KVS_V = 4480, KVS_BYTES = 8576;
constexpr uint32_t OFF_WS = WO_EARLY ? OFF_KVS + 4 * KVS_BYTES : OFF_CH0 + 2 * U_BYTES;
constexpr uint32_t OFF_YT = 163840;
constexpr uint32_t OFF_BAR = 231936;
constexpr uint32_t SMEM_BYTES = OFF_BAR + 512;

enum : uint32_t {
  B_FULL1 = 0, B_EMPTY1 = 4, B_S3 = 7, B_FULL2 = 52, B_EMPTY2 = 13, B_U = 8, B_GATE = 12, B_HA = 19, B_HB = 20,
  B_ATTN = 21, B_C34 = 22, B_CONV = 23, B_YFULL = 24, B_EPOCH = 25, B_PREP = 26, B_P1 = 27, B_LAST = 28,
  B_E3 = 29, B_OSIG = 30, B_WOP = 31, B_USIG = 32, B_WST = 33, B_KV = 34, B_KVD = 39, B_HC = 61, B_QF = 62, B_YST = 40,
  B_TOK = 45, B_YSIG = 50
};
constexpr uint32_t OFF_EPOCH = OFF_BAR + 8 * 51;
__device__ __forceinline__ uint32_t off_o(int j) { return j < 4 ? OFF_OA + j * O_BYTES : j < 6 ? OFF_CH0 + (j - 4) * O_BYTES : OFF_OA + (j - 6) * O_BYTES; }
__device__ __forceinline__ uint32_t off_w(int j) { return j < 4 ? OFF_WA + j * WO_BYTES : j == 4 ? OFF_KVX : j == 5 ? OFF_WC : OFF_WA + (j - 6) * WO_BYTES; }
__device__ __forceinline__ int step_src(int hg, int j) { return SRC_ROT ? (hg + j) & 7 : j == 0 ? hg : j <= hg ? j - 1 : j; }
__device__ __forceinline__ bool tail_first(int hg) { return TAILF && (hg & 3) == 3; }
__device__ __forceinline__ uint32_t off_ch(int c) { return (c < 3 ? OFF_CH0 : OFF_CH3 - 3 * CH_BYTES) + c * CH_BYTES; }

#define U_PITCH 264
__device__ __align__(1024) uint4 g_U[DIM * U_PITCH];
__device__ uint4 g_O[NCTA * 1280];
#define g_Y g_U
constexpr int Y_PITCH = U_PITCH;
__device__ uint4 g_WO[64 * 800];
__device__ uint4 g_halo[NCTA * 2 * 7 * 32];
__device__ float g_gate[SEQ + PAD_KB * 256];
__device__ unsigned g_cnt[32 * (1 + 2 * 16 + 8 + NCTA)];
constexpr int C_LAUNCH = 0, C_PREP = 32, C_Y = 32 * 17, C_W = 32 * 33, C_O = 32 * 41;

#define TSM(cond, slot) do { } while (0)
#define TSIF(cond, slot) do { if (__LINE__ >= FENCE_LO && __LINE__ < FENCE_HI) sched_fence(); } while (0)
__device__ __forceinline__ void sched_fence() {
  asm volatile("{\n.reg .pred p;\n.reg .u32 c;\nmov.u32 c, %%clock;\nsetp.eq.u32 p, c, 0;\n@p st.shared.u32 [%0], c;\n}"
               ::"r"(1024 + OFF_EPOCH + 4) : "memory");
}
#define TS(slot) TSIF(true, slot)

struct Params {
  const __nv_bfloat16 *q, *k, *v, *shift_k, *ssm_k, *ssm_D, *wqkv, *wo, *gate_w;
  __nv_bfloat16* out;
  uint32_t zero;
};

#define POLL_NS 0
constexpr int SPIN_LIMIT = 1 << 17;

__device__ __forceinline__ void mbar_init(uint32_t bar, uint32_t count) {
  asm volatile("mbarrier.init.shared::cta.b64 [%0], %1;" ::"r"(bar), "r"(count) : "memory");
}
__device__ __forceinline__ void mbar_expect_tx(uint32_t bar, uint32_t bytes) {
  asm volatile("mbarrier.arrive.expect_tx.shared::cta.b64 _, [%0], %1;" ::"r"(bar), "r"(bytes) : "memory");
}
__device__ __forceinline__ void mbar_arrive(uint32_t bar) {
  asm volatile("mbarrier.arrive.shared::cta.b64 _, [%0];" ::"r"(bar) : "memory");
}
__device__ __forceinline__ void mbar_wait(uint32_t bar, uint32_t parity) {
  uint32_t ok;
  int spins = 0;
  do {
    if (WAIT_NS)
      asm volatile("{\n.reg .pred p;\nmbarrier.try_wait.parity.shared::cta.b64 p, [%1], %2, %3;\nselp.b32 %0, 1, 0, p;\n}"
                   : "=r"(ok) : "r"(bar), "r"(parity), "r"(WAIT_NS) : "memory");
    else
      asm volatile("{\n.reg .pred p;\nmbarrier.try_wait.parity.shared::cta.b64 p, [%1], %2;\nselp.b32 %0, 1, 0, p;\n}"
                   : "=r"(ok) : "r"(bar), "r"(parity) : "memory");
    if (++spins > SPIN_LIMIT) break;
  } while (!ok);
}
__device__ __forceinline__ void flag_poll(const unsigned* p, unsigned target) {
  unsigned v;
  int spins = 0;
  do {
    if (POLL_NS && spins) __nanosleep(POLL_NS);
    asm volatile("ld.relaxed.gpu.global.u32 %0, [%1];" : "=r"(v) : "l"(p) : "memory");
    if (++spins > SPIN_LIMIT) break;
  } while ((int)(v - target) < 0);
}
__device__ __forceinline__ void flag_wait(const unsigned* p, unsigned target) {
  flag_poll(p, target);
  asm volatile("fence.acquire.gpu;\nfence.proxy.async.global;" ::: "memory");
}
__device__ __forceinline__ void flag_signal(unsigned* p, int n, int lane) {
  if (lane == 0) asm volatile("fence.release.gpu;" ::: "memory");
  __syncwarp();
  if (lane < n) asm volatile("red.relaxed.gpu.global.add.u32 [%0], 1;" ::"l"(p + 32 * lane) : "memory");
}
__device__ __forceinline__ void flag_bump(unsigned* p) {
  asm volatile("red.relaxed.gpu.global.add.u32 [%0], 1;" ::"l"(p) : "memory");
}
__device__ __forceinline__ void fence_async_smem() { asm volatile("fence.proxy.async.shared::cta;" ::: "memory"); }
__device__ __forceinline__ void wg_sync(int id) { asm volatile("bar.sync %0, 128;" ::"r"(id) : "memory"); }

__device__ __forceinline__ void tma_2d(uint32_t dst, const CUtensorMap* tm, int c0, int c1, uint32_t bar) {
  asm volatile("cp.async.bulk.tensor.2d.shared::cluster.global.mbarrier::complete_tx::bytes [%0], [%1, {%3, %4}], [%2];"
               ::"r"(dst), "l"(tm), "r"(bar), "r"(c0), "r"(c1) : "memory");
}
__device__ __forceinline__ void tma_3d(uint32_t dst, const CUtensorMap* tm, int c0, int c1, int c2, uint32_t bar) {
  asm volatile("cp.async.bulk.tensor.3d.shared::cluster.global.mbarrier::complete_tx::bytes [%0], [%1, {%3, %4, %5}], [%2];"
               ::"r"(dst), "l"(tm), "r"(bar), "r"(c0), "r"(c1), "r"(c2) : "memory");
}
__device__ __forceinline__ void bulk_load(uint32_t dst, const void* src, uint32_t bytes, uint32_t bar) {
  asm volatile("cp.async.bulk.shared::cluster.global.mbarrier::complete_tx::bytes [%0], [%1], %2, [%3];"
               ::"r"(dst), "l"(src), "r"(bytes), "r"(bar) : "memory");
}
__device__ __forceinline__ void tm_prefetch(const CUtensorMap* tm) {
  asm volatile("prefetch.tensormap [%0];" ::"l"(tm) : "memory");
}

__device__ __forceinline__ void wg_fence() { asm volatile("wgmma.fence.sync.aligned;" ::: "memory"); }
__device__ __forceinline__ void wg_commit() { asm volatile("wgmma.commit_group.sync.aligned;" ::: "memory"); }
template <int N> __device__ __forceinline__ void wg_wait() { asm volatile("wgmma.wait_group.sync.aligned %0;" ::"n"(N) : "memory"); }
__device__ __forceinline__ uint32_t desc_lo(uint32_t addr, uint32_t lbo) { return ((addr & 0x3FFFF) >> 4) | ((lbo >> 4) << 16); }
constexpr uint32_t desc_hi(uint32_t sbo, uint32_t swz) { return (sbo >> 4) | (swz << 30); }
constexpr uint32_t HI_SW128 = desc_hi(1024, 1), HI_SW64 = desc_hi(512, 2), HI_SW32 = desc_hi(256, 3), HI_NONE = desc_hi(128, 0);
template <int N> __device__ __forceinline__ void pin(float* d) {
#pragma unroll
  for (int i = 0; i < N; i++) asm volatile("" : "+f"(d[i])::"memory");
}

__device__ __forceinline__ uint32_t lds32(uint32_t a) {
  uint32_t v;
  asm volatile("ld.volatile.shared.u32 %0, [%1];" : "=r"(v) : "r"(a) : "memory");
  return v;
}
__device__ __forceinline__ uint4 ldg128(const void* a) {
  uint4 v;
  asm volatile("ld.global.nc.v4.u32 {%0, %1, %2, %3}, [%4];" : "=r"(v.x), "=r"(v.y), "=r"(v.z), "=r"(v.w) : "l"(a) : "memory");
  return v;
}
__device__ __forceinline__ uint2 ldg64(const void* a) {
  uint2 v;
  asm volatile("ld.global.nc.v2.u32 {%0, %1}, [%2];" : "=r"(v.x), "=r"(v.y) : "l"(a) : "memory");
  return v;
}
__device__ __forceinline__ void ldsm4(uint32_t* r, uint32_t a) {
  asm volatile("ldmatrix.sync.aligned.m8n8.x4.shared.b16 {%0, %1, %2, %3}, [%4];"
               : "=r"(r[0]), "=r"(r[1]), "=r"(r[2]), "=r"(r[3]) : "r"(a) : "memory");
}
__device__ __forceinline__ void ldsm4t(uint32_t* r, uint32_t a) {
  asm volatile("ldmatrix.sync.aligned.m8n8.x4.trans.shared.b16 {%0, %1, %2, %3}, [%4];"
               : "=r"(r[0]), "=r"(r[1]), "=r"(r[2]), "=r"(r[3]) : "r"(a) : "memory");
}
__device__ __forceinline__ uint4 lds128(uint32_t a) {
  uint4 v;
  asm volatile("ld.shared.v4.u32 {%0, %1, %2, %3}, [%4];" : "=r"(v.x), "=r"(v.y), "=r"(v.z), "=r"(v.w) : "r"(a) : "memory");
  return v;
}
__device__ __forceinline__ void sts128(uint32_t a, uint32_t x, uint32_t y, uint32_t z, uint32_t w) {
  asm volatile("st.shared.v4.u32 [%0], {%1, %2, %3, %4};" ::"r"(a), "r"(x), "r"(y), "r"(z), "r"(w) : "memory");
}
__device__ __forceinline__ void stsm4(uint32_t a, const uint32_t* r) {
  asm volatile("stmatrix.sync.aligned.m8n8.x4.shared.b16 [%0], {%1, %2, %3, %4};" ::"r"(a), "r"(r[0]), "r"(r[1]), "r"(r[2]), "r"(r[3]) : "memory");
}
__device__ __forceinline__ void stsm4t(uint32_t a, const uint32_t* r) {
  asm volatile("stmatrix.sync.aligned.m8n8.x4.trans.shared.b16 [%0], {%1, %2, %3, %4};" ::"r"(a), "r"(r[0]), "r"(r[1]), "r"(r[2]), "r"(r[3]) : "memory");
}
__device__ __forceinline__ uint32_t pack2(float lo, float hi) {
  uint32_t r;
  asm("cvt.rn.bf16x2.f32 %0, %1, %2;" : "=r"(r) : "f"(hi), "f"(lo));
  return r;
}
__device__ __forceinline__ uint32_t movm(uint32_t a) {
  uint32_t d;
  asm volatile("movmatrix.sync.aligned.m8n8.trans.b16 %0, %1;" : "=r"(d) : "r"(a));
  return d;
}
__device__ __forceinline__ uint32_t bmul(uint32_t a, uint32_t b) {
  uint32_t d;
  asm("mul.rn.bf16x2 %0, %1, %2;" : "=r"(d) : "r"(a), "r"(b));
  return d;
}
__device__ __forceinline__ uint32_t badd(uint32_t a, uint32_t b) {
  uint32_t d;
  asm("add.rn.bf16x2 %0, %1, %2;" : "=r"(d) : "r"(a), "r"(b));
  return d;
}
__device__ __forceinline__ float bf_lo(uint32_t x) { return __uint_as_float(x << 16); }
__device__ __forceinline__ float bf_hi(uint32_t x) { return __uint_as_float(x & 0xFFFF0000u); }
__device__ __forceinline__ float ex2(float x) {
  float y;
  asm("ex2.approx.ftz.f32 %0, %1;" : "=f"(y) : "f"(x));
  return y;
}
__device__ __forceinline__ float rcp(float x) {
  float y;
  asm("rcp.approx.ftz.f32 %0, %1;" : "=f"(y) : "f"(x));
  return y;
}
__device__ __forceinline__ void mma16816(float* d, uint32_t a0, uint32_t a1, uint32_t a2, uint32_t a3, uint32_t b0, uint32_t b1) {
  asm volatile("mma.sync.aligned.m16n8k16.row.col.f32.bf16.bf16.f32 {%0, %1, %2, %3}, {%4, %5, %6, %7}, {%8, %9}, {%0, %1, %2, %3};"
               : "+f"(d[0]), "+f"(d[1]), "+f"(d[2]), "+f"(d[3])
               : "r"(a0), "r"(a1), "r"(a2), "r"(a3), "r"(b0), "r"(b1));
}
__device__ __forceinline__ void mma1688(float* d, uint32_t a0, uint32_t a1, uint32_t b0) {
  asm volatile("mma.sync.aligned.m16n8k8.row.col.f32.bf16.bf16.f32 {%0, %1, %2, %3}, {%4, %5}, {%6}, {%0, %1, %2, %3};"
               : "+f"(d[0]), "+f"(d[1]), "+f"(d[2]), "+f"(d[3])
               : "r"(a0), "r"(a1), "r"(b0));
}

template <int N> struct WgRS;
template <int N> struct WgSST;
template <> struct WgRS<32> {
  template <uint32_t HB>
  static __device__ __forceinline__ void mma(float* d, const uint32_t* a, uint32_t db) {
    asm volatile("{\n.reg .pred p;\n.reg .b64 db;\nsetp.ne.b32 p, %22, 0;\n"
      "mov.b64 db, {%20, %21};\n"
      "wgmma.mma_async.sync.aligned.m64n32k16.f32.bf16.bf16 {"
      "%0, %1, %2, %3, %4, %5, %6, %7, %8, %9, %10, %11, %12, %13, %14, %15"
      "}, {%16, %17, %18, %19}, db, p, 1, 1, 1;\n}\n"
      : "+f"(d[0]), "+f"(d[1]), "+f"(d[2]), "+f"(d[3]), "+f"(d[4]), "+f"(d[5]), "+f"(d[6]), "+f"(d[7]),
        "+f"(d[8]), "+f"(d[9]), "+f"(d[10]), "+f"(d[11]), "+f"(d[12]), "+f"(d[13]), "+f"(d[14]), "+f"(d[15])
      : "r"(a[0]), "r"(a[1]), "r"(a[2]), "r"(a[3]), "r"(db), "n"(HB), "n"(1));
  }
  template <uint32_t HB>
  static __device__ __forceinline__ void set(float* d, const uint32_t* a, uint32_t db) {
    asm volatile("{\n.reg .pred p;\n.reg .b64 db;\nsetp.ne.b32 p, %22, 0;\n"
      "mov.b64 db, {%20, %21};\n"
      "wgmma.mma_async.sync.aligned.m64n32k16.f32.bf16.bf16 {"
      "%0, %1, %2, %3, %4, %5, %6, %7, %8, %9, %10, %11, %12, %13, %14, %15"
      "}, {%16, %17, %18, %19}, db, p, 1, 1, 1;\n}\n"
      : "=f"(d[0]), "=f"(d[1]), "=f"(d[2]), "=f"(d[3]), "=f"(d[4]), "=f"(d[5]), "=f"(d[6]), "=f"(d[7]),
        "=f"(d[8]), "=f"(d[9]), "=f"(d[10]), "=f"(d[11]), "=f"(d[12]), "=f"(d[13]), "=f"(d[14]), "=f"(d[15])
      : "r"(a[0]), "r"(a[1]), "r"(a[2]), "r"(a[3]), "r"(db), "n"(HB), "n"(0));
  }
};
template <> struct WgRS<64> {
  template <uint32_t HB>
  static __device__ __forceinline__ void mma(float* d, const uint32_t* a, uint32_t db) {
    asm volatile("{\n.reg .pred p;\n.reg .b64 db;\nsetp.ne.b32 p, %38, 0;\n"
      "mov.b64 db, {%36, %37};\n"
      "wgmma.mma_async.sync.aligned.m64n64k16.f32.bf16.bf16 {"
      "%0, %1, %2, %3, %4, %5, %6, %7, %8, %9, %10, %11, %12, %13, %14, %15, "
      "%16, %17, %18, %19, %20, %21, %22, %23, %24, %25, %26, %27, %28, %29, %30, %31"
      "}, {%32, %33, %34, %35}, db, p, 1, 1, 1;\n}\n"
      : "+f"(d[0]), "+f"(d[1]), "+f"(d[2]), "+f"(d[3]), "+f"(d[4]), "+f"(d[5]), "+f"(d[6]), "+f"(d[7]),
        "+f"(d[8]), "+f"(d[9]), "+f"(d[10]), "+f"(d[11]), "+f"(d[12]), "+f"(d[13]), "+f"(d[14]), "+f"(d[15]),
        "+f"(d[16]), "+f"(d[17]), "+f"(d[18]), "+f"(d[19]), "+f"(d[20]), "+f"(d[21]), "+f"(d[22]), "+f"(d[23]),
        "+f"(d[24]), "+f"(d[25]), "+f"(d[26]), "+f"(d[27]), "+f"(d[28]), "+f"(d[29]), "+f"(d[30]), "+f"(d[31])
      : "r"(a[0]), "r"(a[1]), "r"(a[2]), "r"(a[3]), "r"(db), "n"(HB), "n"(1));
  }
  template <uint32_t HB>
  static __device__ __forceinline__ void set(float* d, const uint32_t* a, uint32_t db) {
    asm volatile("{\n.reg .pred p;\n.reg .b64 db;\nsetp.ne.b32 p, %38, 0;\n"
      "mov.b64 db, {%36, %37};\n"
      "wgmma.mma_async.sync.aligned.m64n64k16.f32.bf16.bf16 {"
      "%0, %1, %2, %3, %4, %5, %6, %7, %8, %9, %10, %11, %12, %13, %14, %15, "
      "%16, %17, %18, %19, %20, %21, %22, %23, %24, %25, %26, %27, %28, %29, %30, %31"
      "}, {%32, %33, %34, %35}, db, p, 1, 1, 1;\n}\n"
      : "=f"(d[0]), "=f"(d[1]), "=f"(d[2]), "=f"(d[3]), "=f"(d[4]), "=f"(d[5]), "=f"(d[6]), "=f"(d[7]),
        "=f"(d[8]), "=f"(d[9]), "=f"(d[10]), "=f"(d[11]), "=f"(d[12]), "=f"(d[13]), "=f"(d[14]), "=f"(d[15]),
        "=f"(d[16]), "=f"(d[17]), "=f"(d[18]), "=f"(d[19]), "=f"(d[20]), "=f"(d[21]), "=f"(d[22]), "=f"(d[23]),
        "=f"(d[24]), "=f"(d[25]), "=f"(d[26]), "=f"(d[27]), "=f"(d[28]), "=f"(d[29]), "=f"(d[30]), "=f"(d[31])
      : "r"(a[0]), "r"(a[1]), "r"(a[2]), "r"(a[3]), "r"(db), "n"(HB), "n"(0));
  }
};
template <> struct WgSST<48> {
  template <uint32_t HA, uint32_t HB>
  static __device__ __forceinline__ void mma(float* d, uint32_t da, uint32_t db, int sc) {
    asm volatile("{\n.reg .pred p;\n.reg .b64 da, db;\nsetp.ne.b32 p, %28, 0;\n"
      "mov.b64 da, {%24, %25};\nmov.b64 db, {%26, %27};\n"
      "wgmma.mma_async.sync.aligned.m64n48k16.f32.bf16.bf16 {"
      "%0, %1, %2, %3, %4, %5, %6, %7, %8, %9, %10, %11, %12, %13, %14, %15, "
      "%16, %17, %18, %19, %20, %21, %22, %23"
      "}, da, db, p, 1, 1, 0, 1;\n}\n"
      : "+f"(d[0]), "+f"(d[1]), "+f"(d[2]), "+f"(d[3]), "+f"(d[4]), "+f"(d[5]), "+f"(d[6]), "+f"(d[7]),
        "+f"(d[8]), "+f"(d[9]), "+f"(d[10]), "+f"(d[11]), "+f"(d[12]), "+f"(d[13]), "+f"(d[14]), "+f"(d[15]),
        "+f"(d[16]), "+f"(d[17]), "+f"(d[18]), "+f"(d[19]), "+f"(d[20]), "+f"(d[21]), "+f"(d[22]), "+f"(d[23])
      : "r"(da), "n"(HA), "r"(db), "n"(HB), "r"(sc));
  }
};
template <> struct WgSST<80> {
  template <uint32_t HA, uint32_t HB>
  static __device__ __forceinline__ void mma(float* d, uint32_t da, uint32_t db, int sc) {
    asm volatile("{\n.reg .pred p;\n.reg .b64 da, db;\nsetp.ne.b32 p, %44, 0;\n"
      "mov.b64 da, {%40, %41};\nmov.b64 db, {%42, %43};\n"
      "wgmma.mma_async.sync.aligned.m64n80k16.f32.bf16.bf16 {"
      "%0, %1, %2, %3, %4, %5, %6, %7, %8, %9, %10, %11, %12, %13, %14, %15, "
      "%16, %17, %18, %19, %20, %21, %22, %23, %24, %25, %26, %27, %28, %29, %30, %31, "
      "%32, %33, %34, %35, %36, %37, %38, %39"
      "}, da, db, p, 1, 1, 0, 1;\n}\n"
      : "+f"(d[0]), "+f"(d[1]), "+f"(d[2]), "+f"(d[3]), "+f"(d[4]), "+f"(d[5]), "+f"(d[6]), "+f"(d[7]),
        "+f"(d[8]), "+f"(d[9]), "+f"(d[10]), "+f"(d[11]), "+f"(d[12]), "+f"(d[13]), "+f"(d[14]), "+f"(d[15]),
        "+f"(d[16]), "+f"(d[17]), "+f"(d[18]), "+f"(d[19]), "+f"(d[20]), "+f"(d[21]), "+f"(d[22]), "+f"(d[23]),
        "+f"(d[24]), "+f"(d[25]), "+f"(d[26]), "+f"(d[27]), "+f"(d[28]), "+f"(d[29]), "+f"(d[30]), "+f"(d[31]),
        "+f"(d[32]), "+f"(d[33]), "+f"(d[34]), "+f"(d[35]), "+f"(d[36]), "+f"(d[37]), "+f"(d[38]), "+f"(d[39])
      : "r"(da), "n"(HA), "r"(db), "n"(HB), "r"(sc));
  }
};
template <> struct WgSST<192> {
  template <uint32_t HA, uint32_t HB>
  static __device__ __forceinline__ void mma(float* d, uint32_t da, uint32_t db, int sc) {
    asm volatile("{\n.reg .pred p;\n.reg .b64 da, db;\nsetp.ne.b32 p, %100, 0;\n"
      "mov.b64 da, {%96, %97};\nmov.b64 db, {%98, %99};\n"
      "wgmma.mma_async.sync.aligned.m64n192k16.f32.bf16.bf16 {"
      "%0, %1, %2, %3, %4, %5, %6, %7, %8, %9, %10, %11, %12, %13, %14, %15, "
      "%16, %17, %18, %19, %20, %21, %22, %23, %24, %25, %26, %27, %28, %29, %30, %31, "
      "%32, %33, %34, %35, %36, %37, %38, %39, %40, %41, %42, %43, %44, %45, %46, %47, "
      "%48, %49, %50, %51, %52, %53, %54, %55, %56, %57, %58, %59, %60, %61, %62, %63, "
      "%64, %65, %66, %67, %68, %69, %70, %71, %72, %73, %74, %75, %76, %77, %78, %79, "
      "%80, %81, %82, %83, %84, %85, %86, %87, %88, %89, %90, %91, %92, %93, %94, %95"
      "}, da, db, p, 1, 1, 0, 1;\n}\n"
      : "+f"(d[0]), "+f"(d[1]), "+f"(d[2]), "+f"(d[3]), "+f"(d[4]), "+f"(d[5]), "+f"(d[6]), "+f"(d[7]),
        "+f"(d[8]), "+f"(d[9]), "+f"(d[10]), "+f"(d[11]), "+f"(d[12]), "+f"(d[13]), "+f"(d[14]), "+f"(d[15]),
        "+f"(d[16]), "+f"(d[17]), "+f"(d[18]), "+f"(d[19]), "+f"(d[20]), "+f"(d[21]), "+f"(d[22]), "+f"(d[23]),
        "+f"(d[24]), "+f"(d[25]), "+f"(d[26]), "+f"(d[27]), "+f"(d[28]), "+f"(d[29]), "+f"(d[30]), "+f"(d[31]),
        "+f"(d[32]), "+f"(d[33]), "+f"(d[34]), "+f"(d[35]), "+f"(d[36]), "+f"(d[37]), "+f"(d[38]), "+f"(d[39]),
        "+f"(d[40]), "+f"(d[41]), "+f"(d[42]), "+f"(d[43]), "+f"(d[44]), "+f"(d[45]), "+f"(d[46]), "+f"(d[47]),
        "+f"(d[48]), "+f"(d[49]), "+f"(d[50]), "+f"(d[51]), "+f"(d[52]), "+f"(d[53]), "+f"(d[54]), "+f"(d[55]),
        "+f"(d[56]), "+f"(d[57]), "+f"(d[58]), "+f"(d[59]), "+f"(d[60]), "+f"(d[61]), "+f"(d[62]), "+f"(d[63]),
        "+f"(d[64]), "+f"(d[65]), "+f"(d[66]), "+f"(d[67]), "+f"(d[68]), "+f"(d[69]), "+f"(d[70]), "+f"(d[71]),
        "+f"(d[72]), "+f"(d[73]), "+f"(d[74]), "+f"(d[75]), "+f"(d[76]), "+f"(d[77]), "+f"(d[78]), "+f"(d[79]),
        "+f"(d[80]), "+f"(d[81]), "+f"(d[82]), "+f"(d[83]), "+f"(d[84]), "+f"(d[85]), "+f"(d[86]), "+f"(d[87]),
        "+f"(d[88]), "+f"(d[89]), "+f"(d[90]), "+f"(d[91]), "+f"(d[92]), "+f"(d[93]), "+f"(d[94]), "+f"(d[95])
      : "r"(da), "n"(HA), "r"(db), "n"(HB), "r"(sc));
  }
};

struct FftConst {
  uint32_t f[2][4], fi[4][4];
  float ta[4], tb[4];
};
__device__ __forceinline__ void cis(int m, float scale, float& c, float& s) {
  const float a = (float)m * (-6.283185307179586f * scale);
  c = __cosf(a);
  s = __sinf(a);
}
__device__ __forceinline__ void fft_tables(uint32_t (&v)[12], int tw) {
  const int row = tw >> 2, ch = tw & 3;
#pragma unroll
  for (int i = 0; i < 4; i++) {
    float c[2], s[2], x[2];
#pragma unroll
    for (int e = 0; e < 2; e++) {
      cis((((32 * (8 * ch + 2 * i + e) + 15) * (4 * row - 63) + 2048) & 4095) - 2048, 1.f / 4096, c[e], s[e]);
      float gc, gs;
      cis((((row & 15) * (8 * (ch & 1) + 2 * i + e) + 8) & 15) - 8, 1.f / 16, gc, gs);
      x[e] = (row >> 4) == (ch >> 1) ? gc : (ch >> 1) ? gs : -gs;
    }
    v[i] = pack2(c[0] * 0.125f, c[1] * 0.125f);
    v[4 + i] = pack2(s[0] * 0.125f, s[1] * 0.125f);
    v[8 + i] = pack2(x[0], x[1]);
  }
#pragma unroll
  for (int i = 0; i < 12; i++) asm volatile("" : "+r"(v[i]));
}
__device__ __forceinline__ void fft_tables_store(const uint32_t (&v)[12], uint32_t sb, int tw) {
  const int row = tw >> 2;
  const uint32_t x = ((tw ^ (row >> 1)) & 3) << 4, a = sb + OFF_FT + (16 * (row >> 3) + (row & 7)) * 64 + x;
  sts128(a, v[0], v[1], v[2], v[3]);
  sts128(a + 512, v[4], v[5], v[6], v[7]);
  sts128(sb + OFF_GT + row * 64 + x, v[8], v[9], v[10], v[11]);
}
__device__ __forceinline__ void fft_twiddles(FftConst& k, int w, int lane) {
#pragma unroll
  for (int i = 0; i < 4; i++) {
    float c, s;
    cis((2 * (8 * (i >> 1) + 2 * (lane & 3) + (i & 1)) - 15) * (4 * (8 * w + (lane >> 2)) - 63), 1.f / 4096, c, s);
    k.ta[i] = __fdividef(-s, 1.f + c);
    k.tb[i] = s;
  }
  pin<4>(k.ta);
  pin<4>(k.tb);
}
__device__ __forceinline__ void fft_matrices(FftConst& k, uint32_t sb, int w, int lane) {
  const uint32_t x = (lane >> 1) & 3;
#pragma unroll
  for (int i = 0; i < 2; i++) {
    ldsm4(k.f[i], sb + OFF_FT + (16 * w + (lane & 15)) * 64 + (((2 * i + (lane >> 4)) ^ x) << 4));
    ldsm4t(k.fi[i], sb + OFF_FT + (32 * i + lane) * 64 + ((w ^ x) << 4));
#pragma unroll
    for (int j = 0; j < 4; j++) {
      k.fi[2 + i][j] = (j & 1) ? k.fi[i][j - 1] ^ 0x80008000u : k.fi[i][j + 1];
      asm volatile("" : "+r"(k.fi[2 + i][j]));
    }
  }
}
template <bool INV> __device__ __forceinline__ void rot(float& x, float& y, float a, float b) {
  x = fmaf(INV ? -a : a, y, x);
  y = fmaf(INV ? -b : b, x, y);
  x = fmaf(INV ? -a : a, y, x);
}
__device__ __forceinline__ void twiddle_fwd(uint32_t (&a)[4][4], float* d, const FftConst& k) {
#pragma unroll
  for (int q = 0; q < 4; q++)
#pragma unroll
    for (int j = 0; j < 2; j++) {
      float* x = d + 8 * q + 4 * j;
      rot<false>(x[0], x[2], k.ta[2 * j], k.tb[2 * j]);
      rot<false>(x[1], x[3], k.ta[2 * j + 1], k.tb[2 * j + 1]);
      a[q & 2][2 * j + (q & 1)] = pack2(x[0], x[1]);
      a[(q & 2) + 1][2 * j + (q & 1)] = pack2(x[2], x[3]);
    }
}
__device__ __forceinline__ void g_step(float* d, const uint32_t (&a)[4][4], uint32_t dre, uint32_t dim) {
  WgRS<32>::set<HI_SW64>(d, a[0], dre);
  WgRS<32>::set<HI_SW64>(d + 16, a[2], dre);
  WgRS<32>::mma<HI_SW64>(d, a[1], dim);
  WgRS<32>::mma<HI_SW64>(d + 16, a[3], dim);
  wg_commit();
}

__device__ __forceinline__ void conv_channel(const FftConst& k, uint32_t sb, int c, int wg, int w, int lane) {
  const uint32_t cb = sb + off_ch(c), bars = sb + OFF_BAR;
  const uint32_t du = desc_lo(cb, 1024), dg = desc_lo(sb + OFF_GT, 16), dz = desc_lo(cb + U_BYTES, 16);
  float U[32], H[32];
  uint32_t a[4][4], e[4][4];
  const float dv = __uint_as_float(lds32(sb + OFF_D + 4 * c));
  wg_fence();
  WgRS<64>::set<HI_SW32>(H, k.f[0], du + 256);
  WgRS<64>::mma<HI_SW32>(H, k.f[1], du + 256 + 32);
  wg_commit();
  wg_wait<0>();
  pin<32>(H);
  twiddle_fwd(a, H, k);
  if (ATT_GATE && H_EARLY) mbar_wait(bars + 8 * B_ATTN, 0);
  mbar_wait(bars + 8 * (B_U + (c < 3 ? c : 3)), 0);
  TSM(w == 0 && c < 3, 7 + wg);
  if (TOK_G < 8 && c > 0) mbar_wait(bars + 8 * (B_TOK + c - 1), 0);
  wg_fence();
  WgRS<64>::set<HI_SW32>(U, k.f[0], du);
  WgRS<64>::mma<HI_SW32>(U, k.f[1], du + 32);
  wg_commit();
  g_step(H, a, dg, dg + 64);
  wg_wait<1>();
  pin<32>(U);
  if (TOK_G == 1 && lane == 0) mbar_arrive(bars + 8 * (B_TOK + c));
  twiddle_fwd(e, U, k);
  wg_fence();
  g_step(U, e, dg, dg + 64);
  if (TOK_G == 2 && lane == 0) mbar_arrive(bars + 8 * (B_TOK + c));
  wg_wait<0>();
  pin<32>(U);
  pin<32>(H);
#pragma unroll
  for (int j = 0; j < 2; j++) {
    float pr[4][2], pi[4][2];
#pragma unroll
    for (int x = 0; x < 2; x++) {
      H[4 * j + x] += dv;
#pragma unroll
      for (int m = 0; m < 4; m++) {
#pragma unroll
        for (int q = 0; q <= m; q++) {
          const int ih = 16 * (q >> 1) + 2 * (q & 1) + 4 * j + x, iu = 16 * ((m - q) >> 1) + 2 * ((m - q) & 1) + 4 * j + x;
          pr[m][x] = q ? fmaf(H[ih], U[iu], pr[m][x]) : H[ih] * U[iu];
          pi[m][x] = q ? fmaf(H[ih], U[iu + 8], pi[m][x]) : H[ih] * U[iu + 8];
          pr[m][x] = fmaf(-H[ih + 8], U[iu + 8], pr[m][x]);
          pi[m][x] = fmaf(H[ih + 8], U[iu], pi[m][x]);
        }
      }
    }
#pragma unroll
    for (int m = 0; m < 4; m++) {
      a[m & 2][2 * j + (m & 1)] = pack2(pr[m][0], pr[m][1]);
      a[(m & 2) + 1][2 * j + (m & 1)] = pack2(pi[m][0], pi[m][1]);
    }
  }
  wg_fence();
  g_step(U, a, dg + 64, dg);
  if (TOK_G == 3 && lane == 0) mbar_arrive(bars + 8 * (B_TOK + c));
  const uint32_t za = cb + U_BYTES + (8 * w + (lane & 7)) * 128 + (((lane >> 3) ^ (lane & 7)) << 4);
  const uint32_t ya = cb + (lane >> 4) * 1024 + (8 * w + (lane & 7)) * 32 + ((((lane >> 3) ^ (lane >> 2)) & 1) << 4);
  wg_sync(1 + wg);
  wg_wait<0>();
  pin<32>(U);
  TSIF(w == 0, 80 + c);
#pragma unroll
  for (int p = 0; p < 2; p++) {
#pragma unroll
    for (int i = 0; i < 4; i++) {
      const int j = i & 1;
      float* x = U + 16 * p + 4 * j + (i & 2);
      rot<true>(x[8], x[0], k.ta[2 * j], k.tb[2 * j]);
      rot<true>(x[9], x[1], k.ta[2 * j + 1], k.tb[2 * j + 1]);
      e[p][i] = pack2(x[8], x[9]);
      e[2 + p][i] = pack2(x[0], x[1]);
    }
    stsm4(za ^ (64 * p), e[p]);
    stsm4((za ^ (64 * p)) + 4096, e[2 + p]);
  }
  fence_async_smem();
  wg_sync(1 + wg);
  wg_fence();
  WgRS<64>::set<HI_SW128>(H, k.fi[0], dz);
#pragma unroll
  for (int ks = 1; ks < 4; ks++) WgRS<64>::mma<HI_SW128>(H, k.fi[ks], dz + 128 * ks);
  wg_commit();
  wg_wait<0>();
  pin<32>(H);
  TSIF(w == 0, 88 + c);
#pragma unroll
  for (int j = 0; j < 8; j++)
    a[j >> 2][j & 3] = j < 2 ? pack2(H[4 * j], H[4 * j + 1]) : pack2(H[4 * j] + H[4 * j - 6], H[4 * j + 1] + H[4 * j - 5]);
  stsm4(ya, a[0]);
  stsm4(ya + 2048, a[1]);
  fence_async_smem();
  __syncwarp();
}

__device__ __forceinline__ void prep_slab(uint4* res, const uint2* sw, uint32_t sb, int slab, int w, int lane) {
  const int t = lane & 3, tp = (lane & 7) >> 1, pos = 8 * tp + 2 * (((lane >> 3) + tp) & 3) + (lane & 1);
  const uint32_t base = sb + OFF_KVS + slab * KVS_BYTES + pos * 128;
  uint32_t kk[2][4][4], vv[2][4];
  mbar_wait(sb + OFF_BAR + 8 * (B_KV + slab), 0);
#pragma unroll
  for (int h = 0; h < 2; h++) {
#pragma unroll
    for (int j = 0; j < 4; j++) {
      const uint32_t a = base + 128 * j;
      ldsm4t(kk[h][j], a + (((w + 4 * h) ^ ((a >> 7) & 7)) << 4));
    }
    const uint32_t a = base + KVS_V;
    ldsm4t(vv[h], a + (((w + 4 * h) ^ ((a >> 7) & 7)) << 4));
  }
#pragma unroll
  for (int h = 0; h < 2; h++) {
    uint32_t (&k)[4][4] = kk[h];
    uint32_t (&v)[4] = vv[h];
    const uint32_t w0 = __byte_perm(sw[h].x, 0, 0x1010), w1 = __byte_perm(sw[h].x, 0, 0x3232);
    const uint32_t w2 = __byte_perm(sw[h].y, 0, 0x1010), w3 = __byte_perm(sw[h].y, 0, 0x3232);
#pragma unroll
    for (int m = 0; m < 4; m++)
      v[m] = bmul(badd(badd(badd(bmul(k[0][m], w3), bmul(k[1][m], w2)), bmul(k[2][m], w1)), bmul(k[3][m], w0)), v[m]);
    uint32_t a[4];
#pragma unroll
    for (int m = 0; m < 4; m++) a[m] = (t & 1) ? v[(m + 3) & 3] : v[m];
    res[h] = (t & 2) ? make_uint4(a[2], a[3], a[0], a[1]) : make_uint4(a[0], a[1], a[2], a[3]);
  }
}

__device__ __forceinline__ void prep_gate(const Params& p, int b, int w, int lane) {
  uint2 gw[5], x[4][5];
#pragma unroll
  for (int j = 0; j < 5; j++) gw[j] = ldg64(reinterpret_cast<const uint2*>(p.gate_w) + lane + 32 * j);
#pragma unroll
  for (int i = 0; i < 4; i++)
#pragma unroll
    for (int j = 0; j < 5; j++)
      x[i][j] = ldg64(reinterpret_cast<const uint2*>(p.q) + (16 * b + 4 * w + i) * (DIM / 4) + lane + 32 * j);
  float s[4];
#pragma unroll
  for (int i = 0; i < 4; i++) {
    s[i] = 0.f;
#pragma unroll
    for (int j = 0; j < 5; j++) {
      const uint32_t m0 = bmul(x[i][j].x, gw[j].x), m1 = bmul(x[i][j].y, gw[j].y);
      s[i] += (bf_lo(m0) + bf_hi(m0)) + (bf_lo(m1) + bf_hi(m1));
    }
  }
  const bool h = lane & 16, q = lane & 8;
  const float a = (h ? s[2] : s[0]) + __shfl_xor_sync(0xffffffffu, h ? s[0] : s[2], 16);
  const float c = (h ? s[3] : s[1]) + __shfl_xor_sync(0xffffffffu, h ? s[1] : s[3], 16);
  float z = (q ? c : a) + __shfl_xor_sync(0xffffffffu, q ? a : c, 8);
#pragma unroll
  for (int o = 4; o > 0; o >>= 1) z += __shfl_xor_sync(0xffffffffu, z, o);
  z = bf_lo(pack2(z, 0.f));
  if ((lane & 7) == 0) g_gate[16 * b + 4 * w + (lane >> 3)] = bf_lo(pack2(__fdividef(1.f, 1.f + __expf(-z)), 0.f));
}

__device__ __forceinline__ uint32_t bmax(uint32_t a, uint32_t b) {
  uint32_t d;
  asm("max.bf16x2 %0, %1, %2;" : "=r"(d) : "r"(a), "r"(b));
  return d;
}
__device__ __forceinline__ void softmax_two(const float (&l)[2][2], uint32_t& p0, uint32_t& p1) {
  constexpr float kScale = 0.22360679774997896f, kLog2e = 1.4426950408889634f;
  const uint32_t r0 = pack2(l[0][0], l[1][0]), r1 = pack2(l[0][1], l[1][1]);
  const uint32_t x0 = pack2(bf_lo(r0) * kScale, bf_hi(r0) * kScale), x1 = pack2(bf_lo(r1) * kScale, bf_hi(r1) * kScale);
  uint32_t m = bmax(x0, x1);
  m = bmax(m, __shfl_xor_sync(0xffffffffu, m, 1));
  m = bmax(m, __shfl_xor_sync(0xffffffffu, m, 2));
  const float m0 = bf_lo(m) * kLog2e, m1 = bf_hi(m) * kLog2e;
  p0 = pack2(ex2(bf_lo(x0) * kLog2e - m0), ex2(bf_lo(x1) * kLog2e - m0));
  p1 = pack2(ex2(bf_hi(x0) * kLog2e - m1), ex2(bf_hi(x1) * kLog2e - m1));
}

__device__ __forceinline__ void halo_read(uint32_t (&kpv)[10], uint32_t (&vpv)[10], uint32_t (&tg)[7], const uint4* hp) {
#pragma unroll
  for (int j = 0; j < 7; j++) {
    uint32_t x0, x1, x2;
    asm volatile("ld.relaxed.gpu.global.v4.u32 {%0, %1, %2, %3}, [%4];"
                 : "=r"(x0), "=r"(x1), "=r"(x2), "=r"(tg[j]) : "l"(hp + 32 * j) : "memory");
    if (j < 4) kpv[3 * j] = x0; else vpv[3 * j - 10] = x0;
    if (j < 3) kpv[3 * j + 1] = x1; else vpv[3 * j - 9] = x1;
    if (j < 3) kpv[3 * j + 2] = x2; else if (j < 6) vpv[3 * j - 8] = x2;
  }
}

template <int ROT>
__device__ __forceinline__ void pack_qkv(const float* acc, uint32_t (&qlo)[10], uint32_t (&qhi)[10], uint32_t (&klo)[10],
                                         uint32_t (&khi)[10], uint32_t (&vlo)[10], uint32_t (&vhi)[10]) {
#pragma unroll
  for (int j = 0; j < 10; j++) {
    const int x = (j + ROT) % 10, tq = x < 8 ? x : 16 + x, tk = x < 8 ? 8 + x : 18 + x, tv = x < 8 ? 16 + x : 20 + x;
    khi[j] = pack2(acc[4 * tk + 2], acc[4 * tk + 3]);
    vhi[j] = movm(pack2(acc[4 * tv + 2], acc[4 * tv + 3]));
    qlo[j] = pack2(acc[4 * tq], acc[4 * tq + 1]);
    qhi[j] = pack2(acc[4 * tq + 2], acc[4 * tq + 3]);
    klo[j] = pack2(acc[4 * tk], acc[4 * tk + 1]);
    vlo[j] = pack2(acc[4 * tv], acc[4 * tv + 1]);
    asm volatile("" : "+r"(khi[j]), "+r"(qlo[j]), "+r"(qhi[j]), "+r"(klo[j]), "+r"(vlo[j]));
  }
}

__device__ __forceinline__ void attention(float* acc, uint32_t sb, int b, int par, int w, int lane) {
  const int g = lane >> 2, t = lane & 3;
  uint32_t klo[10], khi[10], vlo[10], vhi[10], qlo[10], qhi[10], kpv[10], vpv[10];
  if (tail_first(b & 7)) pack_qkv<8>(acc, qlo, qhi, klo, khi, vlo, vhi);
  else pack_qkv<0>(acc, qlo, qhi, klo, khi, vlo, vhi);
  uint32_t tag = 0;
  if (w == 0 || w == 3) {
    mbar_wait(sb + OFF_BAR + 8 * B_EPOCH, 0);
    tag = lds32(sb + OFF_EPOCH) + 1;
  }
  const uint32_t xa = sb + OFF_KVX + (par * 3) * 2560 + lane * 16;
  if (w < 3) {
    mbar_wait(sb + OFF_BAR + 8 * B_S3, 0);
    sts128(xa + w * 2560, khi[0], khi[1], khi[2], khi[3]);
    sts128(xa + w * 2560 + 512, khi[4], khi[5], khi[6], khi[7]);
    sts128(xa + w * 2560 + 1024, khi[8], khi[9], vhi[0], vhi[1]);
    sts128(xa + w * 2560 + 1536, vhi[2], vhi[3], vhi[4], vhi[5]);
    sts128(xa + w * 2560 + 2048, vhi[6], vhi[7], vhi[8], vhi[9]);
  } else if (b < NCTA - 8) {
    uint4* ho = g_halo + (b * 2 + par) * 224 + lane;
#pragma unroll
    for (int j = 0; j < 7; j++) {
      const uint32_t x0 = j < 4 ? khi[3 * j] : vhi[3 * j - 10], x1 = j < 3 ? khi[3 * j + 1] : vhi[3 * j - 9];
      const uint32_t x2 = j < 3 ? khi[3 * j + 2] : j < 6 ? vhi[3 * j - 8] : 0u;
      asm volatile("st.relaxed.gpu.global.v4.u32 [%0], {%1, %2, %3, %4};" ::"l"(ho + 32 * j), "r"(x0), "r"(x1), "r"(x2), "r"(tag) : "memory");
    }
  }
  TSIF(par == 0 && w == 1, 64);
  TSIF(par == 0 && w == 3, 76);
#pragma unroll
  for (int j = 0; j < 10; j++) vlo[j] = movm(vlo[j]);
  const bool far0 = 2 * t > g, far1 = 2 * t + 1 > g;
  const uint32_t mfar = (far0 ? 0x0000FFFFu : 0u) | (far1 ? 0xFFFF0000u : 0u);
  float slo[4][2], shi[4][2], lg[2][2];
  uint32_t phi[4], plo[4], qml[4], qmh[4];
#pragma unroll
  for (int h = 0; h < 4; h++) {
    const int f = h == 0 ? 0 : h == 1 ? 3 : h == 2 ? 5 : 8, hf = h < 2 ? 2 : 7;
    const bool mine = (h & 1) ? t >= 2 : t < 2;
    qml[h] = mine ? qlo[hf] : 0u;
    qmh[h] = mine ? qhi[hf] : 0u;
    float a[4] = {0.f, 0.f, 0.f, 0.f}, c[4] = {0.f, 0.f, 0.f, 0.f};
    mma16816(a, qlo[f], qhi[f], qlo[f + 1], qhi[f + 1], klo[f], klo[f + 1]);
    mma16816(c, qlo[f], qhi[f], qlo[f + 1], qhi[f + 1], khi[f], khi[f + 1]);
    mma1688(a, qml[h], qmh[h], klo[hf]);
    mma1688(c, qml[h], qmh[h], khi[hf]);
    slo[h][0] = a[0];
    slo[h][1] = a[1];
    shi[h][0] = lg[h & 1][0] = far0 ? a[2] : c[2];
    shi[h][1] = lg[h & 1][1] = far1 ? a[3] : c[3];
    if (!ATT_MERGE && (h & 1)) softmax_two(lg, phi[h - 1], phi[h]);
  }
  TSIF(par == 0 && w == 1, 65);
  wg_sync(1 + par);
  TSIF(par == 0 && w == 1, 66);
  const bool nohist = (w == 0) && (b < 8);
  const uint4* hp = g_halo + ((b - 8) * 2 + par) * 224 + lane;
  uint32_t tg[7];
  if (w > 0) {
    const uint4 v0 = lds128(xa + (w - 1) * 2560), v1 = lds128(xa + (w - 1) * 2560 + 512), v2 = lds128(xa + (w - 1) * 2560 + 1024);
    const uint4 v3 = lds128(xa + (w - 1) * 2560 + 1536), v4 = lds128(xa + (w - 1) * 2560 + 2048);
    kpv[0] = v0.x; kpv[1] = v0.y; kpv[2] = v0.z; kpv[3] = v0.w; kpv[4] = v1.x; kpv[5] = v1.y; kpv[6] = v1.z; kpv[7] = v1.w;
    kpv[8] = v2.x; kpv[9] = v2.y; vpv[0] = v2.z; vpv[1] = v2.w; vpv[2] = v3.x; vpv[3] = v3.y; vpv[4] = v3.z; vpv[5] = v3.w;
    vpv[6] = v4.x; vpv[7] = v4.y; vpv[8] = v4.z; vpv[9] = v4.w;
  } else if (nohist) {
#pragma unroll
    for (int j = 0; j < 10; j++) kpv[j] = vpv[j] = 0u;
  } else {
    TSIF(par == 0, 77);
    halo_read(kpv, vpv, tg, hp);
  }
  if (w == 0 && !nohist) {
    int spins = 0;
    while (true) {
      bool ok = true;
#pragma unroll
      for (int j = 0; j < 7; j++) ok = ok && tg[j] == tag;
      if (__all_sync(0xffffffffu, ok) || ++spins > SPIN_LIMIT) break;
      halo_read(kpv, vpv, tg, hp);
    }
    TSIF(par == 0, 79);
  }
#pragma unroll
  for (int h = 0; h < 4; h++) {
    const int f = h == 0 ? 0 : h == 1 ? 3 : h == 2 ? 5 : 8, hf = h < 2 ? 2 : 7;
    float a[4] = {0.f, 0.f, 0.f, 0.f};
    mma16816(a, qlo[f], qhi[f], qlo[f + 1], qhi[f + 1], kpv[f], kpv[f + 1]);
    mma1688(a, qml[h], qmh[h], kpv[hf]);
    const float ninf = __int_as_float(0xff800000);
    lg[h & 1][0] = far0 ? (nohist ? ninf : a[0]) : slo[h][0];
    lg[h & 1][1] = far1 ? (nohist ? ninf : a[1]) : slo[h][1];
    if (h & 1) {
      softmax_two(lg, plo[h - 1], plo[h]);
      if (ATT_MERGE) {
        const float lh[2][2] = {{shi[h - 1][0], shi[h - 1][1]}, {shi[h][0], shi[h][1]}};
        softmax_two(lh, phi[h - 1], phi[h]);
      }
    }
  }
  TSIF(par == 0 && w <= 1, 67 + w);
  uint32_t ov[20];
#pragma unroll
  for (int hp = 0; hp < 2; hp++) {
    const int hf = hp ? 7 : 2;
    float sh[4] = {0.f, 0.f, 0.f, 0.f}, i0 = 0.f, i1 = 0.f;
#pragma unroll
    for (int e = 0; e < 2; e++) {
      const int h = 2 * hp + e, f = h == 0 ? 0 : h == 1 ? 3 : h == 2 ? 5 : 8;
      const uint32_t a0 = plo[h] & mfar, a2 = plo[h] & ~mfar, a3 = phi[h] & mfar, c1 = phi[h] & ~mfar;
      float sum[4] = {0.f, 0.f, 0.f, 0.f};
      mma1688(sum, plo[h], phi[h], 0x3F803F80u);
      const float r0 = rcp(sum[0]), r1 = rcp(sum[2]);
#pragma unroll
      for (int j = f; j < f + 2; j++) {
        float o[4] = {0.f, 0.f, 0.f, 0.f};
        mma16816(o, a0, 0u, a2, a3, vpv[j], vlo[j]);
        mma1688(o, 0u, c1, vhi[j]);
        ov[2 * j] = pack2(o[0] * r0, o[1] * r0);
        ov[2 * j + 1] = pack2(o[2] * r1, o[3] * r1);
      }
      const bool mine = e ? g >= 4 : g < 4;
      mma16816(sh, a0, 0u, a2, a3, mine ? vpv[hf] : 0u, mine ? vlo[hf] : 0u);
      mma1688(sh, 0u, c1, mine ? vhi[hf] : 0u);
      if (e == 0 || t >= 2) {
        i0 = r0;
        i1 = r1;
      }
    }
    ov[2 * hf] = pack2(sh[0] * i0, sh[1] * i0);
    ov[2 * hf + 1] = pack2(sh[2] * i1, sh[3] * i1);
  }
  TS(32 + 4 * par + w);
  mbar_wait(sb + OFF_BAR + 8 * B_P1, 0);
  const uint32_t oa = sb + OFF_OA + (lane >> 4) * 2048 + (32 * w + 2 * (lane & 15) + par) * 16;
#pragma unroll
  for (int j = 0; j < 5; j++) stsm4(oa + 4096 * j, ov + 4 * j);
  TSIF(par == 0 && w == 0, 120);
  fence_async_smem();
  TSIF(par == 0 && w == 0, 121);
  __syncwarp();
  if (lane == 0) mbar_arrive(sb + OFF_BAR + 8 * B_ATTN);
  TSIF(par == 0 && w == 0, 122);
}

struct Maps {
  CUtensorMap x, wm, wt, k, v, y, wo, qm, qt, om, ot;
};

__device__ __forceinline__ void load_stage(uint32_t sb, int kb, int b, const Maps& m) {
  const uint32_t st = sb + (kb & 3) * STAGE_BYTES, bar = sb + OFF_BAR + 8 * (B_FULL1 + (kb & 3));
  const int r = b >> 3, hg = b & 7, slab = kb - KV_KB;
  const bool kv = slab >= 0 && slab < 5;
  const uint32_t kbar = sb + OFF_BAR + 8 * (B_KV + slab), dst = sb + OFF_KVS + slab * KVS_BYTES;
  mbar_expect_tx(bar, STAGE_BYTES);
  if (kv) mbar_expect_tx(kbar, KVS_BYTES);
  tma_3d(st, &m.x, 64 * kb, 64 * r, 0, bar);
  if (kv && KV_MIX) tma_3d(dst, &m.k, 0, 32 * (b >> 1) - 3, 2 * slab + (b & 1), kbar);
  tma_3d(st + ST_W, &m.wm, 80 * hg + (tail_first(hg) ? 16 : 0), 64 * kb, 0, bar);
  if (kv && KV_MIX) tma_3d(dst + KVS_V, &m.v, 0, 32 * (b >> 1), 2 * slab + (b & 1), kbar);
  tma_3d(st + ST_WT, &m.wt, 80 * hg + (tail_first(hg) ? 0 : 64), 64 * kb, 0, bar);
  if (kv && !KV_MIX) tma_3d(dst, &m.k, 0, 32 * (b >> 1) - 3, 2 * slab + (b & 1), kbar);
  if (kv && !KV_MIX) tma_3d(dst + KVS_V, &m.v, 0, 32 * (b >> 1), 2 * slab + (b & 1), kbar);
}

__global__ void __launch_bounds__(NTHR, 1) fused_kernel(const __grid_constant__ Maps m, const Params p) {
  extern __shared__ __align__(1024) uint8_t smem[];
  const uint32_t sb = (uint32_t)__cvta_generic_to_shared(smem);
  const uint32_t bars = sb + OFF_BAR;
  const int tid = threadIdx.x, lane = tid & 31;
  int b = blockIdx.x;
  if (BMAP == 1) b = (((b & 63) >> 3) * 2 + (b & 1)) * 8 + (((b < 64 ? 0x6521 : 0x7430) >> (4 * ((b >> 1) & 3))) & 7);
  if (BMAP == 2) b = ((b & 63) >> 2) * 8 + (((b < 64 ? 0x6521 : 0x7430) >> (4 * (b & 3))) & 7);
  if (BMAP == 3) b = (((b & 63) >> 3) * 2 + (b & 1)) * 8 + (((b < 64 ? 0x7430 : 0x6521) >> (4 * ((b >> 1) & 3))) & 7);
  if (BMAP == 4) b = (((b >> 4) * 2 + (b & 1)) * 8) + ((b >> 1) & 7);
  if (BMAP == 5) b = 127 - b;
  const int r = b >> 3, hg = b & 7;

  if (tid == T_ISSUE) {
    TSM(true, 0);
#pragma unroll
    for (int i = 0; i < 4; i++) mbar_init(bars + 8 * (B_FULL1 + i), 1);
#pragma unroll
    for (int i = 0; i < 3; i++) mbar_init(bars + 8 * (B_KV + i), 1);
    fence_async_smem();
#pragma unroll 1
    for (int kb = 0; kb <= PRE2; kb++) load_stage(sb, kb, b, m);
  } else if (tid >= T_PF && tid < T_PF + 11) {
    tm_prefetch(&m.x + (tid - T_PF));
  } else if (tid == T_INIT) {
#pragma unroll
    for (int i = 0; i < 4; i++) mbar_init(bars + 8 * (B_EMPTY1 + i), 8);
#pragma unroll
    for (int i = 0; i < 8; i++) mbar_init(bars + 8 * (B_FULL2 + i), 1);
#pragma unroll
    for (int i = 0; i < 4; i++) mbar_init(bars + 8 * (B_EMPTY2 + i), 8);
#pragma unroll
    for (int i = 0; i < 4; i++) mbar_init(bars + 8 * (B_U + i), 1);
    mbar_init(bars + 8 * B_HA, 4);
    mbar_init(bars + 8 * B_GATE, 4);
    mbar_init(bars + 8 * B_HB, 1);
    mbar_init(bars + 8 * B_KVD, 4);
    mbar_init(bars + 8 * B_QF, 1);
    mbar_init(bars + 8 * B_ATTN, 8);
    mbar_init(bars + 8 * B_P1, 8);
    mbar_init(bars + 8 * B_C34, 1);
#pragma unroll
    for (int i = 0; i < 5; i++) mbar_init(bars + 8 * (B_YST + i), 4);
#pragma unroll
    for (int i = 0; i < 5; i++) mbar_init(bars + 8 * (B_TOK + i), 4);
    mbar_init(bars + 8 * B_YSIG, 1);
    mbar_init(bars + 8 * B_YFULL, 1);
    mbar_init(bars + 8 * B_EPOCH, 1);
    mbar_init(bars + 8 * B_PREP, 4);
    mbar_init(bars + 8 * B_USIG, 1);
    mbar_init(bars + 8 * B_WST, 1);
#pragma unroll
    for (int i = 3; i < 5; i++) mbar_init(bars + 8 * (B_KV + i), 1);
    mbar_init(bars + 8 * B_E3, 8);
    mbar_init(bars + 8 * B_LAST, 1);
    mbar_init(bars + 8 * B_OSIG, 1);
    mbar_init(bars + 8 * B_WOP, 1);
    fence_async_smem();
  }
  const int warp = __shfl_sync(0xffffffffu, tid >> 5, 0), wg = warp >> 2, w = warp & 3;
  __syncthreads();

  if (wg == 3) {
    asm volatile("setmaxnreg.dec.sync.aligned.u32 56;");
    if (w == 0) {
      if (lane == 0) {
#pragma unroll 1
        for (int kb = 1 + PRE2; kb < 10; kb++) {
          if (kb >= 4) mbar_wait(bars + 8 * (kb == 7 ? B_E3 : B_EMPTY1 + (kb & 3)), (kb >> 3) & 1);
          TSIF(kb >= 4, 44 + kb);
          if (WO_EARLY && kb == KV_KB + 4) mbar_wait(bars + 8 * B_WOP, 0);
          load_stage(sb, kb, b, m);
          if (kb == TRIG_KB) mbar_arrive(bars + 8 * B_LAST);
          if (WO_EARLY && kb == WO_EARLY) {
            mbar_expect_tx(bars + 8 * B_WST, WO_BYTES / 2);
            tma_3d(sb + OFF_WS, &m.wo, 0, 40 * r, 5 * hg, bars + 8 * B_WST);
          }
        }
        mbar_wait(bars + 8 * B_P1, 0);
        mbar_wait(bars + 8 * WL_TRIG, 0);
        mbar_wait(bars + 8 * B_EPOCH, 0);
        flag_wait(g_cnt + C_W + 32 * hg, (lds32(sb + OFF_EPOCH) + 1) * 16);
        TS(30);
#pragma unroll 1
        for (int j = 0; j < 8; j++) {
          if (j >= 6) mbar_wait(bars + 8 * (B_EMPTY2 + j - 6), 0);
          if (j == 4) mbar_wait(bars + 8 * B_ATTN, 0);
          TSIF(j >= 6, 100 + j);
          if (RF_GATE && j == 6) mbar_wait(bars + 8 * B_YSIG, 0);
          mbar_expect_tx(bars + 8 * (B_FULL2 + j), j == 0 ? WO_BYTES : j == 5 ? O_BYTES + WO_BYTES + 512 : O_BYTES + WO_BYTES);
          bulk_load(sb + off_w(j), g_WO + (hg * 8 + step_src(hg, j)) * 800, WO_BYTES, bars + 8 * (B_FULL2 + j));
        }
        mbar_wait(bars + 8 * (B_EMPTY2 + 3), 0);
        mbar_expect_tx(bars + 8 * B_QF, O_BYTES);
        tma_2d(sb + OFF_QS, &m.qm, 80 * hg, 128 * r, bars + 8 * B_QF);
        tma_2d(sb + OFF_QT, &m.qt, 80 * hg + 64, 128 * r, bars + 8 * B_QF);
      }
    } else if (w == 1) {
      unsigned epoch = 0;
      if (lane == 0) {
        epoch = atomicAdd(g_cnt + C_LAUNCH, 1u) / NCTA;
        asm volatile("st.shared.u32 [%0], %1;" ::"r"(sb + OFF_EPOCH), "r"(epoch) : "memory");
        mbar_arrive(bars + 8 * B_EPOCH);
        mbar_wait(bars + 8 * B_KVD, 0);
        mbar_expect_tx(bars + 8 * B_HB, 5 * 4096);
#pragma unroll 1
        for (int c = 0; c < 5; c++) {
          if (c == 3) mbar_wait(bars + 8 * B_S3, 0);
          bulk_load(sb + off_ch(c) + U_BYTES, p.ssm_k + (5 * b + c) * SEQ, 4096, bars + 8 * B_HB);
        }
#pragma unroll
        for (int c = 0; c < 4; c++) mbar_expect_tx(bars + 8 * (B_U + c), c < 3 ? U_BYTES : 2 * U_BYTES);
        const uint4* usrc = g_U + 5 * b * U_PITCH;
        mbar_wait(bars + 8 * B_USIG, 0);
        flag_wait(g_cnt + C_PREP + 32 * (b & 15), (epoch + 1) * NCTA);
        TS(23);
#pragma unroll
        for (int c = 0; c < 5; c++) {
          if (c == 3) mbar_wait(bars + 8 * (B_U + 2), 0);
          if (c == 1) mbar_wait(bars + 8 * B_WOP, 0);
          bulk_load(sb + off_ch(c), usrc + c * U_PITCH, U_BYTES, bars + 8 * (B_U + (c < 3 ? c : 3)));
          TSIF(c == 0 || c == 4, 116 + (c >> 2));
        }
      }
      epoch = __shfl_sync(0xffffffffu, epoch, 0);
      if (lane < 8) {
        const int src = (b & ~7) | step_src(hg, lane);
        mbar_wait(bars + 8 * B_OSIG, 0);
        flag_wait(g_cnt + C_O + 32 * src, epoch + 1);
        if (lane >= 1 && lane < 4) bulk_load(sb + off_o(lane), g_O + src * 1280, O_BYTES, bars + 8 * (B_FULL2 + lane));
        __syncwarp(0xff);
        TS(21);
        if (lane == 5) bulk_load(sb + OFF_GATE, g_gate + 128 * r, 512, bars + 8 * (B_FULL2 + 5));
#pragma unroll 1
        for (int j = 4; j < 8; j++) {
          if (lane == j) {
            mbar_wait(bars + 8 * (j < 6 ? B_C34 : B_EMPTY2 + j - 6), 0);
            if (RF_GATE && j == 6) mbar_wait(bars + 8 * B_YSIG, 0);
            bulk_load(sb + off_o(j), g_O + src * 1280, O_BYTES, bars + 8 * (B_FULL2 + j));
          }
          __syncwarp(0xff);
        }
        TS(22);
      }
    } else if (w == 2) {
      mbar_wait(bars + 8 * B_PREP, 0);
      flag_signal(g_cnt + C_PREP, 16, lane);
      TS(25);
      if (lane == 0) mbar_arrive(bars + 8 * B_USIG);
      mbar_wait(bars + 8 * B_GATE, 0);
      if ((NOMB & 1) && lane == 0) asm volatile("fence.release.gpu;" ::: "memory");
      mbar_wait(bars + 8 * B_ATTN, 0);
      if (lane == 0) {
        if (O_DEFER) mbar_wait(bars + 8 * (B_U + 3), 0);
        asm volatile("cp.async.bulk.global.shared::cta.bulk_group [%0], [%1], 20480;\ncp.async.bulk.commit_group;\n"
                     "cp.async.bulk.wait_group 0;\nfence.proxy.async.global;" ::"l"(g_O + b * 1280), "r"(sb + OFF_OA) : "memory");
      }
      if (!(NOMB & 1)) flag_signal(g_cnt + C_O + 32 * b, 1, lane);
      else if (lane == 0) flag_bump(g_cnt + C_O + 32 * b);
      TS(26);
      if (lane == 0) mbar_arrive(bars + 8 * B_OSIG);
      if (!(NOMB & 4)) {
        mbar_wait(bars + 8 * B_WOP, 0);
        flag_signal(g_cnt + C_W + 32 * hg, 1, lane);
      }
      TS(73);
    } else {
      if (lane == 0) {
        if (!WO_EARLY) {
          mbar_wait(bars + 8 * B_KVD, 0);
          mbar_wait(bars + 8 * WB_TRIG, 0);
          mbar_expect_tx(bars + 8 * B_WST, WO_BYTES / 2);
          tma_3d(sb + OFF_WS, &m.wo, 0, 40 * r, 5 * hg, bars + 8 * B_WST);
        }
        mbar_wait(bars + 8 * B_WST, 0);
        mbar_wait(bars + 8 * WO_TRIG, 0);
        uint4* dst = g_WO + (hg * 8 + (r >> 1)) * 800 + (r & 1) * 80;
#pragma unroll 1
        for (int n = 0; n < 5; n++)
          asm volatile("cp.async.bulk.global.shared::cta.bulk_group [%0], [%1], 1280;" ::"l"(dst + 160 * n), "r"(sb + OFF_WS + 1280 * n) : "memory");
        asm volatile("cp.async.bulk.commit_group;\ncp.async.bulk.wait_group 0;\nfence.proxy.async.global;" ::: "memory");
        if (NOMB & 4) flag_bump(g_cnt + C_W + 32 * hg);
        mbar_arrive(bars + 8 * B_WOP);
      }
      TS(71);
      if (lane == 0) {
#pragma unroll 1
        for (int c = 0; c < 5; c++) {
          mbar_wait(bars + 8 * (B_YST + c), 0);
          asm volatile("cp.async.bulk.global.shared::cta.bulk_group [%0], [%1], 4096;\ncp.async.bulk.commit_group;"
                       ::"l"(g_Y + (5 * b + c) * Y_PITCH), "r"(sb + off_ch(c)) : "memory");
          if (c == 2) {
            asm volatile("cp.async.bulk.wait_group.read 0;" ::: "memory");
            mbar_arrive(bars + 8 * B_C34);
          }
        }
        asm volatile("cp.async.bulk.wait_group 0;\nfence.proxy.async.global;" ::: "memory");
        if (!(NOMB & 2)) asm volatile("fence.release.gpu;" ::: "memory");
        flag_bump(g_cnt + C_Y + 32 * (b >> 4));
        TS(27);
        mbar_arrive(bars + 8 * B_YSIG);
        mbar_expect_tx(bars + 8 * B_YFULL, 20480);
        flag_wait(g_cnt + C_Y + 32 * hg, (lds32(sb + OFF_EPOCH) + 1) * 16);
        TS(24);
        tma_2d(sb + OFF_YT, &m.y, 128 * r, 80 * hg, bars + 8 * B_YFULL);
        tma_2d(sb + OFF_YT + 10240, &m.y, 128 * r + 64, 80 * hg, bars + 8 * B_YFULL);
      }
    }
  } else {
    asm volatile("setmaxnreg.inc.sync.aligned.u32 152;");
    if (wg < 2) {
      float acc[120];
#pragma unroll
      for (int i = 0; i < 120; i++) acc[i] = 0.f;
      const uint32_t da = desc_lo(sb + wg * 8192, 16), db = desc_lo(sb + ST_W, 8192), dc = desc_lo(sb + ST_WT, 2048);
      if (PW1) pin<120>(acc);
      if (PW1 == 2) mbar_wait(bars + 8 * B_FULL1, 0);
#pragma unroll 1
      for (int kb = 0; kb < 10; kb++) {
        mbar_wait(bars + 8 * (B_FULL1 + (kb & 3)), (kb >> 2) & 1);
        const uint32_t so = (kb & 3) * (STAGE_BYTES >> 4);
        wg_fence();
#pragma unroll
        for (int k = 0; k < 4; k++) {
          WgSST<192>::mma<HI_SW128, HI_SW128>(acc, da + so + 2 * k, db + so + 128 * k, 1);
          WgSST<48>::mma<HI_SW128, HI_SW32>(acc + 96, da + so + 2 * k, dc + so + 32 * k, 1);
        }
        wg_commit();
        wg_wait<1>();
        if (kb > 0 && lane == 0) mbar_arrive(bars + 8 * (kb == 4 ? B_E3 : B_EMPTY1 + ((kb - 1) & 3)));
      }
      wg_wait<0>();
      pin<120>(acc);
      if (lane == 0) mbar_arrive(bars + 8 * B_P1);
      TSM(w == 0, 3 + wg);
      attention(acc, sb, b, wg, w, lane);
    } else {
      const int tw = tid & 127, chl = 64 * (b & 1) + 8 * w + (lane >> 2);
      uint4* up = g_U + chl * U_PITCH + ((4 * (b >> 1) + (lane & 3)) ^ ((b >> 2) & 1));
      uint2 sw[10];
      uint32_t dv = 0;
      if (lane < 5) dv = __ldg(reinterpret_cast<const unsigned short*>(p.ssm_D) + 5 * b + lane);
#pragma unroll
      for (int i = 0; i < 10; i++) sw[i] = ldg64(reinterpret_cast<const uint2*>(p.shift_k) + chl + 128 * (i >> 1) + 32 * (i & 1));
      uint32_t tab[12];
      fft_tables(tab, tw);
      uint4 res[10];
#pragma unroll
      for (int i = 0; i < 10; i++) res[i] = make_uint4(0, 0, 0, 0);
#pragma unroll 1
      for (int slab = 0; slab < 5; slab++) {
#pragma unroll
        for (int i = 0; i < 8; i++) res[i] = res[i + 2];
        prep_slab(res + 8, sw, sb, slab, w, lane);
        TSIF(w == 0, 99 + 4 * slab);
#pragma unroll
        for (int i = 0; i < 8; i++) sw[i] = sw[i + 2];
      }
      TSIF(w == 0, 28);
      __syncwarp();
      if (lane == 0) mbar_arrive(bars + 8 * B_KVD + ((res[8].x ^ res[9].x) & p.zero));
      mbar_wait(bars + 8 * B_KVD, 0);
      fft_tables_store(tab, sb, tw);
      mbar_wait(bars + 8 * B_LAST, 0);
#pragma unroll
      for (int i = 0; i < 10; i++) up[(128 * (i >> 1) + 32 * (i & 1)) * U_PITCH] = res[i];
      __syncwarp();
      if (lane == 0) mbar_arrive(bars + 8 * B_PREP);
      TSIF(w == 0, 5);
      mbar_wait(bars + 8 * (G_AFTER ? B_USIG : B_LAST), 0);
      prep_gate(p, b, w, lane);
      __syncwarp();
      if (lane == 0) mbar_arrive(bars + 8 * B_GATE);
      TSIF(w == 0, 72);
      mbar_wait(bars + 8 * B_HB, 0);
      TSIF(w == 0, 123);
      const uint32_t ha = sb + U_BYTES + ((tw >> 3) * 16 + 8 + (tw & 7)) * 16;
      uint4 hv[5];
#pragma unroll
      for (int c = 0; c < 5; c++) hv[c] = lds128(ha + off_ch(c));
      __syncwarp();
#pragma unroll
      for (int c = 0; c < 5; c++) sts128((ha ^ 16) + off_ch(c), hv[c].x, hv[c].y, hv[c].z, hv[c].w);
      if (tw < 5) asm volatile("st.shared.f32 [%0], %1;" ::"r"(sb + OFF_D + 4 * tw), "f"(bf_lo(dv) * 0.125f) : "memory");
      fence_async_smem();
      __syncwarp();
      if (lane == 0) mbar_arrive(bars + 8 * B_HA);
      TSIF(w == 0, 6);
    }

    FftConst fc;
    fft_twiddles(fc, w, lane);
    mbar_wait(bars + 8 * B_HA, 0);
    fft_matrices(fc, sb, w, lane);
    if (ATT_GATE && !H_EARLY) mbar_wait(bars + 8 * B_ATTN, 0);
    TSIF(w == 0 && wg == 2, 124);
#pragma unroll 1
    for (int c = wg == 2 ? 0 : wg + 1; c < 5; c += 3) {
      conv_channel(fc, sb, c, wg, w, lane);
      if (lane == 0) mbar_arrive(bars + 8 * (B_YST + c));
      TSM(w == 0, 10 + c);
    }

    if (wg < 2) {
      const int g = lane >> 2;
      float acc[40];
#pragma unroll
      for (int i = 0; i < 40; i++) acc[i] = 0.f;
      const uint32_t da = desc_lo(sb + wg * 1024, 2048), db = desc_lo(sb, 2560);
      mbar_wait(bars + 8 * B_ATTN, 0);
      mbar_wait(bars + 8 * (B_YST + 3), 0);
      mbar_wait(bars + 8 * (B_YST + 4), 0);
      if (PW2) mbar_wait(bars + 8 * B_FULL2, 0);
#pragma unroll 1
      for (int j = 0; j < 8; j++) {
        mbar_wait(bars + 8 * (B_FULL2 + j), 0);
        const uint32_t oa = da + (off_o(j) >> 4), ob = db + (off_w(j) >> 4);
        wg_fence();
#pragma unroll
        for (int k = 0; k < 5; k++) WgSST<80>::mma<HI_NONE, HI_SW32>(acc, oa + 256 * k, ob + 32 * k, 1);
        wg_commit();
        wg_wait<1>();
        if (j >= 1 && j <= 4 && lane == 0) mbar_arrive(bars + 8 * (B_EMPTY2 + j - 1));
      }
      TSIF(w == 0 && wg == 0, 113);
      const int tr = 64 * wg + 16 * w + (lane & 15);
      const uint32_t fm = sb + OFF_QS + tr * 128, fx = (lane >> 4) ^ (tr & 7);
      const uint32_t ft = sb + OFF_QT + tr * 32 + (((lane >> 4) ^ (tr >> 2)) & 1) * 16;
      const float g0 = __uint_as_float(lds32(sb + OFF_GATE + (64 * wg + 16 * w + g) * 4));
      const float g1 = __uint_as_float(lds32(sb + OFF_GATE + (64 * wg + 16 * w + 8 + g) * 4));
      const uint32_t ga = pack2(g0, g0), gb = pack2(g1, g1);
      const uint32_t na = pack2(1.f - g0, 1.f - g0), nb = pack2(1.f - g1, 1.f - g1);

      wg_wait<0>();
      pin<40>(acc);
      TSM(w == 0, 17 + wg);
      uint32_t pb[20];
#pragma unroll
      for (int j = 0; j < 10; j++) {
        pb[2 * j] = bmul(na, pack2(acc[4 * j], acc[4 * j + 1]));
        pb[2 * j + 1] = bmul(nb, pack2(acc[4 * j + 2], acc[4 * j + 3]));
        asm volatile("" : "+r"(pb[2 * j]), "+r"(pb[2 * j + 1]));
      }
      const uint32_t ya = sb + OFF_YT + wg * 10240 + ((lane >> 4) * 8 + (lane & 7)) * 128 +
                          (((2 * w + (((lane >> 3) & 1) ^ wg)) ^ (lane & 7)) << 4);
      uint32_t qf[20];
      mbar_wait(bars + 8 * B_QF, 0);
#pragma unroll
      for (int j = 0; j < 5; j++) ldsm4(qf + 4 * j, j < 4 ? fm + ((fx ^ (2 * j)) << 4) : ft);
      mbar_wait(bars + 8 * B_YFULL, 0);
      TSIF(w == 0 && wg == 0, 19);
#pragma unroll
      for (int j = 0; j < 5; j++) {
        uint32_t y[4];
        ldsm4t(y, ya + 2048 * j);
#pragma unroll
        for (int i = 0; i < 4; i++) qf[4 * j + i] = badd(bmul((i & 1) ? gb : ga, bmul(qf[4 * j + i], y[i])), pb[4 * j + i]);
      }
#pragma unroll
      for (int j = 0; j < 5; j++) stsm4(j < 4 ? fm + ((fx ^ (2 * j)) << 4) : ft, qf + 4 * j);
      fence_async_smem();
      __syncwarp();
      if (lane == 0) {
        const int row = 64 * wg + 16 * w;
        asm volatile("cp.async.bulk.tensor.2d.global.shared::cta.bulk_group [%0, {%2, %3}], [%1];"
                     ::"l"(&m.om), "r"(sb + OFF_QS + row * 128), "r"(80 * hg), "r"(128 * r + row) : "memory");
        asm volatile("cp.async.bulk.tensor.2d.global.shared::cta.bulk_group [%0, {%2, %3}], [%1];"
                     ::"l"(&m.ot), "r"(sb + OFF_QT + row * 32), "r"(80 * hg + 64), "r"(128 * r + row) : "memory");
        asm volatile("cp.async.bulk.commit_group;\ncp.async.bulk.wait_group.read 0;" ::: "memory");
      }
      TSM(true, 40 + 4 * wg + w);
      if (ENDBAR) asm volatile("bar.sync 15, 256;" ::: "memory");
    }
  }
}

typedef CUresult (*EncodeFn)(CUtensorMap*, CUtensorMapDataType, cuuint32_t, void*, const cuuint64_t*, const cuuint64_t*,
                             const cuuint32_t*, const cuuint32_t*, CUtensorMapInterleave, CUtensorMapSwizzle,
                             CUtensorMapL2promotion, CUtensorMapFloatOOBfill);

void encode(EncodeFn fn, CUtensorMap* tm, const void* base, int rank, const cuuint64_t* dims, const cuuint64_t* strides,
            const cuuint32_t* box, CUtensorMapSwizzle swz) {
  const cuuint32_t ones[3] = {1, 1, 1};
  fn(tm, CU_TENSOR_MAP_DATA_TYPE_BFLOAT16, rank, const_cast<void*>(base), dims, strides, box, ones,
     CU_TENSOR_MAP_INTERLEAVE_NONE, swz, CU_TENSOR_MAP_L2_PROMOTION_L2_128B, CU_TENSOR_MAP_FLOAT_OOB_FILL_NONE);
}

}

extern "C" void kernel_launch(void* const* d_in, const int* in_sizes, int n_in, void* d_out, int out_size) {
  (void)in_sizes; (void)n_in; (void)out_size;
  Params p;
  p.q = (const __nv_bfloat16*)d_in[0];
  p.k = (const __nv_bfloat16*)d_in[1];
  p.v = (const __nv_bfloat16*)d_in[2];
  p.shift_k = (const __nv_bfloat16*)d_in[3];
  p.ssm_k = (const __nv_bfloat16*)d_in[4];
  p.ssm_D = (const __nv_bfloat16*)d_in[5];
  p.wqkv = (const __nv_bfloat16*)d_in[7];
  p.wo = (const __nv_bfloat16*)d_in[8];
  p.gate_w = (const __nv_bfloat16*)d_in[9];
  p.out = (__nv_bfloat16*)d_out;
  p.zero = 0;

  static EncodeFn fn = nullptr;
  static void* yaddr = nullptr;
  if (!fn) {
    cudaDriverEntryPointQueryResult qr;
    void* f = nullptr;
    cudaGetDriverEntryPoint("cuTensorMapEncodeTiled", &f, cudaEnableDefault, &qr);
    fn = (EncodeFn)f;
    cudaGetSymbolAddress(&yaddr, g_Y);
    cudaFuncSetAttribute(fused_kernel, cudaFuncAttributeMaxDynamicSharedMemorySize, SMEM_BYTES);
  }
  Maps m;
  {
    const cuuint64_t dims[3] = {640, 1024, 2}, st[2] = {2560, 1280};
    const cuuint32_t box[3] = {64, 64, 2};
    encode(fn, &m.x, p.q, 3, dims, st, box, CU_TENSOR_MAP_SWIZZLE_128B);
  }
  {
    const cuuint64_t dims[3] = {640, 640, 3}, st[2] = {3840, 1280};
    const cuuint32_t box[3] = {64, 64, 3}, boxt[3] = {16, 64, 3};
    encode(fn, &m.wm, p.wqkv, 3, dims, st, box, CU_TENSOR_MAP_SWIZZLE_128B);
    encode(fn, &m.wt, p.wqkv, 3, dims, st, boxt, CU_TENSOR_MAP_SWIZZLE_32B);
  }
  {
    const cuuint64_t dims[3] = {64, 2048, 10}, st[2] = {1280, 128};
    const cuuint32_t boxk[3] = {64, 35, 1}, boxv[3] = {64, 32, 1};
    encode(fn, &m.k, p.k, 3, dims, st, boxk, CU_TENSOR_MAP_SWIZZLE_128B);
    encode(fn, &m.v, p.v, 3, dims, st, boxv, CU_TENSOR_MAP_SWIZZLE_128B);
  }
  {
    const cuuint64_t dims[3] = {16, 640, 40}, st[2] = {1280, 32};
    const cuuint32_t box[3] = {16, 40, 5};
    encode(fn, &m.wo, p.wo, 3, dims, st, box, CU_TENSOR_MAP_SWIZZLE_32B);
  }
  {
    const cuuint64_t dims[2] = {2048, 640}, st[1] = {Y_PITCH * 16};
    const cuuint32_t box[2] = {64, 80};
    encode(fn, &m.y, yaddr, 2, dims, st, box, CU_TENSOR_MAP_SWIZZLE_128B);
  }
  {
    const cuuint64_t dims[2] = {640, 2048}, st[1] = {1280};
    const cuuint32_t bqm[2] = {64, 128}, bqt[2] = {16, 128}, bom[2] = {64, 16}, bot[2] = {16, 16};
    encode(fn, &m.qm, p.q, 2, dims, st, bqm, CU_TENSOR_MAP_SWIZZLE_128B);
    encode(fn, &m.qt, p.q, 2, dims, st, bqt, CU_TENSOR_MAP_SWIZZLE_32B);
    encode(fn, &m.om, p.out, 2, dims, st, bom, CU_TENSOR_MAP_SWIZZLE_128B);
    encode(fn, &m.ot, p.out, 2, dims, st, bot, CU_TENSOR_MAP_SWIZZLE_32B);
  }
  fused_kernel<<<NCTA, NTHR, SMEM_BYTES>>>(m, p);
}
```

```cpp
#include <cuda.h>
#include <cuda_bf16.h>
#include <cuda_runtime.h>
#include <stdint.h>

namespace {

constexpr int SEQ = 2048, DIM = 640, NCTA = 128, NTHR = 512;

#define TRIG_KB 9
#define KV_KB 2
#define DEV_EXIT 0
#define ATT_GATE 1
#define G_AFTER 0
#define FENCE_LO 0
#define FENCE_HI 0
#define PW1 2
#define PW2 1
#define ENDBAR 0
#define PAD_KB 0
#define Y_ALIAS 1
#define H_EARLY 1
#define RDBK 1
#define NOMB 7
#define WO_EARLY 0
#define SRC_ROT 0
#define WAIT_NS 0
#define WB_TRIG B_USIG
#define G_POS 0
#define TAILF 1
#define T_ISSUE 384
#define T_PF 416
#define T_INIT 448
#define ATT_MERGE 0
#define BMAP 1
#define PRE2 1
#define KV_MIX 0
#define O_DEFER 0
#define TOK_G 1
#define RF_GATE 0
#define WO_TRIG B_WST
#define WL_TRIG B_P1
#define WO_GATE 1

constexpr uint32_t STAGE_BYTES = 47104, ST_W = 16384, ST_WT = 40960;
constexpr uint32_t O_BYTES = 20480, WO_BYTES = 12800;
constexpr uint32_t OFF_OA = 0;
constexpr uint32_t OFF_QS = 3 * O_BYTES, OFF_QT = OFF_QS + 16384;
constexpr uint32_t OFF_WC = 81920;
constexpr uint32_t OFF_WA = 94720;
constexpr uint32_t OFF_GATE = 145920;
constexpr uint32_t OFF_KVX = 147968;
constexpr uint32_t OFF_D = OFF_GATE + 512;
constexpr uint32_t OFF_CH3 = 163840;
constexpr uint32_t CH_BYTES = 12288, U_BYTES = 4096;
constexpr uint32_t OFF_FT = 225280, OFF_GT = 229376;
constexpr uint32_t OFF_CH0 = 188416;
constexpr uint32_t OFF_KVS = OFF_CH0, KVS_V = 4480, KVS_BYTES = 8576;
constexpr uint32_t OFF_WS = WO_EARLY ? OFF_KVS + 4 * KVS_BYTES : OFF_CH0 + 2 * U_BYTES;
constexpr uint32_t OFF_YT = 163840;
constexpr uint32_t OFF_BAR = 231936;
constexpr uint32_t SMEM_BYTES = OFF_BAR + 512;

enum : uint32_t {
  B_FULL1 = 0, B_EMPTY1 = 4, B_S3 = 7, B_FULL2 = 52, B_EMPTY2 = 13, B_U = 8, B_GATE = 12, B_HA = 19, B_HB = 20,
  B_ATTN = 21, B_C34 = 22, B_CONV = 23, B_YFULL = 24, B_EPOCH = 25, B_PREP = 26, B_P1 = 27, B_LAST = 28,
  B_E3 = 29, B_OSIG = 30, B_WOP = 31, B_USIG = 32, B_WST = 33, B_KV = 34, B_KVD = 39, B_HC = 61, B_QF = 62, B_YST = 40,
  B_TOK = 45, B_YSIG = 50
};
constexpr uint32_t OFF_EPOCH = OFF_BAR + 8 * 51;
__device__ __forceinline__ uint32_t off_o(int j) { return j < 4 ? OFF_OA + j * O_BYTES : j < 6 ? OFF_CH0 + (j - 4) * O_BYTES : OFF_OA + (j - 6) * O_BYTES; }
__device__ __forceinline__ uint32_t off_w(int j) { return j < 4 ? OFF_WA + j * WO_BYTES : j == 4 ? OFF_KVX : j == 5 ? OFF_WC : OFF_WA + (j - 6) * WO_BYTES; }
__device__ __forceinline__ int step_src(int hg, int j) { return SRC_ROT ? (hg + j) & 7 : j == 0 ? hg : j <= hg ? j - 1 : j; }
__device__ __forceinline__ bool tail_first(int hg) { return TAILF && (hg & 3) == 3; }
__device__ __forceinline__ uint32_t off_ch(int c) { return (c < 3 ? OFF_CH0 : OFF_CH3 - 3 * CH_BYTES) + c * CH_BYTES; }

#define U_PITCH 264
__device__ __align__(1024) uint4 g_U[DIM * U_PITCH];
__device__ uint4 g_O[NCTA * 1280];
#define g_Y g_U
constexpr int Y_PITCH = U_PITCH;
__device__ uint4 g_WO[64 * 800];
__device__ uint4 g_halo[NCTA * 2 * 7 * 32];
__device__ float g_gate[SEQ + PAD_KB * 256];
__device__ unsigned g_cnt[32 * (1 + 2 * 16 + 8 + NCTA)];
constexpr int C_LAUNCH = 0, C_PREP = 32, C_Y = 32 * 17, C_W = 32 * 33, C_O = 32 * 41;

#define TSM(cond, slot) do { } while (0)
#define TSIF(cond, slot) do { if (__LINE__ >= FENCE_LO && __LINE__ < FENCE_HI) sched_fence(); } while (0)
__device__ __forceinline__ void sched_fence() {
  asm volatile("{\n.reg .pred p;\n.reg .u32 c;\nmov.u32 c, %%clock;\nsetp.eq.u32 p, c, 0;\n@p st.shared.u32 [%0], c;\n}"
               ::"r"(1024 + OFF_EPOCH + 4) : "memory");
}
#define TS(slot) TSIF(true, slot)

struct Params {
  const __nv_bfloat16 *q, *k, *v, *shift_k, *ssm_k, *ssm_D, *wqkv, *wo, *gate_w;
  __nv_bfloat16* out;
  uint32_t zero;
};

#define POLL_NS 0
constexpr int SPIN_LIMIT = 1 << 17;

__device__ __forceinline__ void mbar_init(uint32_t bar, uint32_t count) {
  asm volatile("mbarrier.init.shared::cta.b64 [%0], %1;" ::"r"(bar), "r"(count) : "memory");
}
__device__ __forceinline__ void mbar_expect_tx(uint32_t bar, uint32_t bytes) {
  asm volatile("mbarrier.arrive.expect_tx.shared::cta.b64 _, [%0], %1;" ::"r"(bar), "r"(bytes) : "memory");
}
__device__ __forceinline__ void mbar_arrive(uint32_t bar) {
  asm volatile("mbarrier.arrive.shared::cta.b64 _, [%0];" ::"r"(bar) : "memory");
}
__device__ __forceinline__ void mbar_wait(uint32_t bar, uint32_t parity) {
  uint32_t ok;
  int spins = 0;
  do {
    if (WAIT_NS)
      asm volatile("{\n.reg .pred p;\nmbarrier.try_wait.parity.shared::cta.b64 p, [%1], %2, %3;\nselp.b32 %0, 1, 0, p;\n}"
                   : "=r"(ok) : "r"(bar), "r"(parity), "r"(WAIT_NS) : "memory");
    else
      asm volatile("{\n.reg .pred p;\nmbarrier.try_wait.parity.shared::cta.b64 p, [%1], %2;\nselp.b32 %0, 1, 0, p;\n}"
                   : "=r"(ok) : "r"(bar), "r"(parity) : "memory");
    if (++spins > SPIN_LIMIT) break;
  } while (!ok);
}
__device__ __forceinline__ void flag_poll(const unsigned* p, unsigned target) {
  unsigned v;
  int spins = 0;
  do {
    if (POLL_NS && spins) __nanosleep(POLL_NS);
    asm volatile("ld.relaxed.gpu.global.u32 %0, [%1];" : "=r"(v) : "l"(p) : "memory");
    if (++spins > SPIN_LIMIT) break;
  } while ((int)(v - target) < 0);
}
__device__ __forceinline__ void flag_wait(const unsigned* p, unsigned target) {
  flag_poll(p, target);
  asm volatile("fence.acquire.gpu;\nfence.proxy.async.global;" ::: "memory");
}
__device__ __forceinline__ void flag_signal(unsigned* p, int n, int lane) {
  if (lane == 0) asm volatile("fence.release.gpu;" ::: "memory");
  __syncwarp();
  if (lane < n) asm volatile("red.relaxed.gpu.global.add.u32 [%0], 1;" ::"l"(p + 32 * lane) : "memory");
}
__device__ __forceinline__ unsigned read_back(const void* p) {
  unsigned v = 0;
  if (RDBK) asm volatile("ld.relaxed.gpu.global.u32 %0, [%1];" : "=r"(v) : "l"(p) : "memory");
  return v;
}
__device__ __forceinline__ void flag_bump(unsigned* p) {
  asm volatile("red.relaxed.gpu.global.add.u32 [%0], 1;" ::"l"(p) : "memory");
}
__device__ __forceinline__ void fence_async_smem() { asm volatile("fence.proxy.async.shared::cta;" ::: "memory"); }
__device__ __forceinline__ void wg_sync(int id) { asm volatile("bar.sync %0, 128;" ::"r"(id) : "memory"); }

__device__ __forceinline__ void tma_2d(uint32_t dst, const CUtensorMap* tm, int c0, int c1, uint32_t bar) {
  asm volatile("cp.async.bulk.tensor.2d.shared::cluster.global.mbarrier::complete_tx::bytes [%0], [%1, {%3, %4}], [%2];"
               ::"r"(dst), "l"(tm), "r"(bar), "r"(c0), "r"(c1) : "memory");
}
__device__ __forceinline__ void tma_3d(uint32_t dst, const CUtensorMap* tm, int c0, int c1, int c2, uint32_t bar) {
  asm volatile("cp.async.bulk.tensor.3d.shared::cluster.global.mbarrier::complete_tx::bytes [%0], [%1, {%3, %4, %5}], [%2];"
               ::"r"(dst), "l"(tm), "r"(bar), "r"(c0), "r"(c1), "r"(c2) : "memory");
}
__device__ __forceinline__ void bulk_load(uint32_t dst, const void* src, uint32_t bytes, uint32_t bar) {
  asm volatile("cp.async.bulk.shared::cluster.global.mbarrier::complete_tx::bytes [%0], [%1], %2, [%3];"
               ::"r"(dst), "l"(src), "r"(bytes), "r"(bar) : "memory");
}
__device__ __forceinline__ void tm_prefetch(const CUtensorMap* tm) {
  asm volatile("prefetch.tensormap [%0];" ::"l"(tm) : "memory");
}

__device__ __forceinline__ void wg_fence() { asm volatile("wgmma.fence.sync.aligned;" ::: "memory"); }
__device__ __forceinline__ void wg_commit() { asm volatile("wgmma.commit_group.sync.aligned;" ::: "memory"); }
template <int N> __device__ __forceinline__ void wg_wait() { asm volatile("wgmma.wait_group.sync.aligned %0;" ::"n"(N) : "memory"); }
__device__ __forceinline__ uint32_t desc_lo(uint32_t addr, uint32_t lbo) { return ((addr & 0x3FFFF) >> 4) | ((lbo >> 4) << 16); }
constexpr uint32_t desc_hi(uint32_t sbo, uint32_t swz) { return (sbo >> 4) | (swz << 30); }
constexpr uint32_t HI_SW128 = desc_hi(1024, 1), HI_SW64 = desc_hi(512, 2), HI_SW32 = desc_hi(256, 3), HI_NONE = desc_hi(128, 0);
template <int N> __device__ __forceinline__ void pin(float* d) {
#pragma unroll
  for (int i = 0; i < N; i++) asm volatile("" : "+f"(d[i])::"memory");
}

__device__ __forceinline__ uint32_t lds32(uint32_t a) {
  uint32_t v;
  asm volatile("ld.volatile.shared.u32 %0, [%1];" : "=r"(v) : "r"(a) : "memory");
  return v;
}
__device__ __forceinline__ uint4 ldg128(const void* a) {
  uint4 v;
  asm volatile("ld.global.nc.v4.u32 {%0, %1, %2, %3}, [%4];" : "=r"(v.x), "=r"(v.y), "=r"(v.z), "=r"(v.w) : "l"(a) : "memory");
  return v;
}
__device__ __forceinline__ uint2 ldg64(const void* a) {
  uint2 v;
  asm volatile("ld.global.nc.v2.u32 {%0, %1}, [%2];" : "=r"(v.x), "=r"(v.y) : "l"(a) : "memory");
  return v;
}
__device__ __forceinline__ void ldsm4(uint32_t* r, uint32_t a) {
  asm volatile("ldmatrix.sync.aligned.m8n8.x4.shared.b16 {%0, %1, %2, %3}, [%4];"
               : "=r"(r[0]), "=r"(r[1]), "=r"(r[2]), "=r"(r[3]) : "r"(a) : "memory");
}
__device__ __forceinline__ void ldsm4t(uint32_t* r, uint32_t a) {
  asm volatile("ldmatrix.sync.aligned.m8n8.x4.trans.shared.b16 {%0, %1, %2, %3}, [%4];"
               : "=r"(r[0]), "=r"(r[1]), "=r"(r[2]), "=r"(r[3]) : "r"(a) : "memory");
}
__device__ __forceinline__ uint4 lds128(uint32_t a) {
  uint4 v;
  asm volatile("ld.shared.v4.u32 {%0, %1, %2, %3}, [%4];" : "=r"(v.x), "=r"(v.y), "=r"(v.z), "=r"(v.w) : "r"(a) : "memory");
  return v;
}
__device__ __forceinline__ void sts128(uint32_t a, uint32_t x, uint32_t y, uint32_t z, uint32_t w) {
  asm volatile("st.shared.v4.u32 [%0], {%1, %2, %3, %4};" ::"r"(a), "r"(x), "r"(y), "r"(z), "r"(w) : "memory");
}
__device__ __forceinline__ void stsm4(uint32_t a, const uint32_t* r) {
  asm volatile("stmatrix.sync.aligned.m8n8.x4.shared.b16 [%0], {%1, %2, %3, %4};" ::"r"(a), "r"(r[0]), "r"(r[1]), "r"(r[2]), "r"(r[3]) : "memory");
}
__device__ __forceinline__ void stsm4t(uint32_t a, const uint32_t* r) {
  asm volatile("stmatrix.sync.aligned.m8n8.x4.trans.shared.b16 [%0], {%1, %2, %3, %4};" ::"r"(a), "r"(r[0]), "r"(r[1]), "r"(r[2]), "r"(r[3]) : "memory");
}
__device__ __forceinline__ uint32_t pack2(float lo, float hi) {
  uint32_t r;
  asm("cvt.rn.bf16x2.f32 %0, %1, %2;" : "=r"(r) : "f"(hi), "f"(lo));
  return r;
}
__device__ __forceinline__ uint32_t movm(uint32_t a) {
  uint32_t d;
  asm volatile("movmatrix.sync.aligned.m8n8.trans.b16 %0, %1;" : "=r"(d) : "r"(a));
  return d;
}
__device__ __forceinline__ uint32_t bmul(uint32_t a, uint32_t b) {
  uint32_t d;
  asm("mul.rn.bf16x2 %0, %1, %2;" : "=r"(d) : "r"(a), "r"(b));
  return d;
}
__device__ __forceinline__ uint32_t badd(uint32_t a, uint32_t b) {
  uint32_t d;
  asm("add.rn.bf16x2 %0, %1, %2;" : "=r"(d) : "r"(a), "r"(b));
  return d;
}
__device__ __forceinline__ float bf_lo(uint32_t x) { return __uint_as_float(x << 16); }
__device__ __forceinline__ float bf_hi(uint32_t x) { return __uint_as_float(x & 0xFFFF0000u); }
__device__ __forceinline__ float ex2(float x) {
  float y;
  asm("ex2.approx.ftz.f32 %0, %1;" : "=f"(y) : "f"(x));
  return y;
}
__device__ __forceinline__ float rcp(float x) {
  float y;
  asm("rcp.approx.ftz.f32 %0, %1;" : "=f"(y) : "f"(x));
  return y;
}
__device__ __forceinline__ void mma16816(float* d, uint32_t a0, uint32_t a1, uint32_t a2, uint32_t a3, uint32_t b0, uint32_t b1) {
  asm volatile("mma.sync.aligned.m16n8k16.row.col.f32.bf16.bf16.f32 {%0, %1, %2, %3}, {%4, %5, %6, %7}, {%8, %9}, {%0, %1, %2, %3};"
               : "+f"(d[0]), "+f"(d[1]), "+f"(d[2]), "+f"(d[3])
               : "r"(a0), "r"(a1), "r"(a2), "r"(a3), "r"(b0), "r"(b1));
}
__device__ __forceinline__ void mma1688(float* d, uint32_t a0, uint32_t a1, uint32_t b0) {
  asm volatile("mma.sync.aligned.m16n8k8.row.col.f32.bf16.bf16.f32 {%0, %1, %2, %3}, {%4, %5}, {%6}, {%0, %1, %2, %3};"
               : "+f"(d[0]), "+f"(d[1]), "+f"(d[2]), "+f"(d[3])
               : "r"(a0), "r"(a1), "r"(b0));
}

template <int N> struct WgRS;
template <int N> struct WgSST;
template <> struct WgRS<32> {
  template <uint32_t HB>
  static __device__ __forceinline__ void mma(float* d, const uint32_t* a, uint32_t db) {
    asm volatile("{\n.reg .pred p;\n.reg .b64 db;\nsetp.ne.b32 p, %22, 0;\n"
      "mov.b64 db, {%20, %21};\n"
      "wgmma.mma_async.sync.aligned.m64n32k16.f32.bf16.bf16 {"
      "%0, %1, %2, %3, %4, %5, %6, %7, %8, %9, %10, %11, %12, %13, %14, %15"
      "}, {%16, %17, %18, %19}, db, p, 1, 1, 1;\n}\n"
      : "+f"(d[0]), "+f"(d[1]), "+f"(d[2]), "+f"(d[3]), "+f"(d[4]), "+f"(d[5]), "+f"(d[6]), "+f"(d[7]),
        "+f"(d[8]), "+f"(d[9]), "+f"(d[10]), "+f"(d[11]), "+f"(d[12]), "+f"(d[13]), "+f"(d[14]), "+f"(d[15])
      : "r"(a[0]), "r"(a[1]), "r"(a[2]), "r"(a[3]), "r"(db), "n"(HB), "n"(1));
  }
  template <uint32_t HB>
  static __device__ __forceinline__ void set(float* d, const uint32_t* a, uint32_t db) {
    asm volatile("{\n.reg .pred p;\n.reg .b64 db;\nsetp.ne.b32 p, %22, 0;\n"
      "mov.b64 db, {%20, %21};\n"
      "wgmma.mma_async.sync.aligned.m64n32k16.f32.bf16.bf16 {"
      "%0, %1, %2, %3, %4, %5, %6, %7, %8, %9, %10, %11, %12, %13, %14, %15"
      "}, {%16, %17, %18, %19}, db, p, 1, 1, 1;\n}\n"
      : "=f"(d[0]), "=f"(d[1]), "=f"(d[2]), "=f"(d[3]), "=f"(d[4]), "=f"(d[5]), "=f"(d[6]), "=f"(d[7]),
        "=f"(d[8]), "=f"(d[9]), "=f"(d[10]), "=f"(d[11]), "=f"(d[12]), "=f"(d[13]), "=f"(d[14]), "=f"(d[15])
      : "r"(a[0]), "r"(a[1]), "r"(a[2]), "r"(a[3]), "r"(db), "n"(HB), "n"(0));
  }
};
template <> struct WgRS<64> {
  template <uint32_t HB>
  static __device__ __forceinline__ void mma(float* d, const uint32_t* a, uint32_t db) {
    asm volatile("{\n.reg .pred p;\n.reg .b64 db;\nsetp.ne.b32 p, %38, 0;\n"
      "mov.b64 db, {%36, %37};\n"
      "wgmma.mma_async.sync.aligned.m64n64k16.f32.bf16.bf16 {"
      "%0, %1, %2, %3, %4, %5, %6, %7, %8, %9, %10, %11, %12, %13, %14, %15, "
      "%16, %17, %18, %19, %20, %21, %22, %23, %24, %25, %26, %27, %28, %29, %30, %31"
      "}, {%32, %33, %34, %35}, db, p, 1, 1, 1;\n}\n"
      : "+f"(d[0]), "+f"(d[1]), "+f"(d[2]), "+f"(d[3]), "+f"(d[4]), "+f"(d[5]), "+f"(d[6]), "+f"(d[7]),
        "+f"(d[8]), "+f"(d[9]), "+f"(d[10]), "+f"(d[11]), "+f"(d[12]), "+f"(d[13]), "+f"(d[14]), "+f"(d[15]),
        "+f"(d[16]), "+f"(d[17]), "+f"(d[18]), "+f"(d[19]), "+f"(d[20]), "+f"(d[21]), "+f"(d[22]), "+f"(d[23]),
        "+f"(d[24]), "+f"(d[25]), "+f"(d[26]), "+f"(d[27]), "+f"(d[28]), "+f"(d[29]), "+f"(d[30]), "+f"(d[31])
      : "r"(a[0]), "r"(a[1]), "r"(a[2]), "r"(a[3]), "r"(db), "n"(HB), "n"(1));
  }
  template <uint32_t HB>
  static __device__ __forceinline__ void set(float* d, const uint32_t* a, uint32_t db) {
    asm volatile("{\n.reg .pred p;\n.reg .b64 db;\nsetp.ne.b32 p, %38, 0;\n"
      "mov.b64 db, {%36, %37};\n"
      "wgmma.mma_async.sync.aligned.m64n64k16.f32.bf16.bf16 {"
      "%0, %1, %2, %3, %4, %5, %6, %7, %8, %9, %10, %11, %12, %13, %14, %15, "
      "%16, %17, %18, %19, %20, %21, %22, %23, %24, %25, %26, %27, %28, %29, %30, %31"
      "}, {%32, %33, %34, %35}, db, p, 1, 1, 1;\n}\n"
      : "=f"(d[0]), "=f"(d[1]), "=f"(d[2]), "=f"(d[3]), "=f"(d[4]), "=f"(d[5]), "=f"(d[6]), "=f"(d[7]),
        "=f"(d[8]), "=f"(d[9]), "=f"(d[10]), "=f"(d[11]), "=f"(d[12]), "=f"(d[13]), "=f"(d[14]), "=f"(d[15]),
        "=f"(d[16]), "=f"(d[17]), "=f"(d[18]), "=f"(d[19]), "=f"(d[20]), "=f"(d[21]), "=f"(d[22]), "=f"(d[23]),
        "=f"(d[24]), "=f"(d[25]), "=f"(d[26]), "=f"(d[27]), "=f"(d[28]), "=f"(d[29]), "=f"(d[30]), "=f"(d[31])
      : "r"(a[0]), "r"(a[1]), "r"(a[2]), "r"(a[3]), "r"(db), "n"(HB), "n"(0));
  }
};
template <> struct WgSST<48> {
  template <uint32_t HA, uint32_t HB>
  static __device__ __forceinline__ void mma(float* d, uint32_t da, uint32_t db, int sc) {
    asm volatile("{\n.reg .pred p;\n.reg .b64 da, db;\nsetp.ne.b32 p, %28, 0;\n"
      "mov.b64 da, {%24, %25};\nmov.b64 db, {%26, %27};\n"
      "wgmma.mma_async.sync.aligned.m64n48k16.f32.bf16.bf16 {"
      "%0, %1, %2, %3, %4, %5, %6, %7, %8, %9, %10, %11, %12, %13, %14, %15, "
      "%16, %17, %18, %19, %20, %21, %22, %23"
      "}, da, db, p, 1, 1, 0, 1;\n}\n"
      : "+f"(d[0]), "+f"(d[1]), "+f"(d[2]), "+f"(d[3]), "+f"(d[4]), "+f"(d[5]), "+f"(d[6]), "+f"(d[7]),
        "+f"(d[8]), "+f"(d[9]), "+f"(d[10]), "+f"(d[11]), "+f"(d[12]), "+f"(d[13]), "+f"(d[14]), "+f"(d[15]),
        "+f"(d[16]), "+f"(d[17]), "+f"(d[18]), "+f"(d[19]), "+f"(d[20]), "+f"(d[21]), "+f"(d[22]), "+f"(d[23])
      : "r"(da), "n"(HA), "r"(db), "n"(HB), "r"(sc));
  }
};
template <> struct WgSST<80> {
  template <uint32_t HA, uint32_t HB>
  static __device__ __forceinline__ void mma(float* d, uint32_t da, uint32_t db, int sc) {
    asm volatile("{\n.reg .pred p;\n.reg .b64 da, db;\nsetp.ne.b32 p, %44, 0;\n"
      "mov.b64 da, {%40, %41};\nmov.b64 db, {%42, %43};\n"
      "wgmma.mma_async.sync.aligned.m64n80k16.f32.bf16.bf16 {"
      "%0, %1, %2, %3, %4, %5, %6, %7, %8, %9, %10, %11, %12, %13, %14, %15, "
      "%16, %17, %18, %19, %20, %21, %22, %23, %24, %25, %26, %27, %28, %29, %30, %31, "
      "%32, %33, %34, %35, %36, %37, %38, %39"
      "}, da, db, p, 1, 1, 0, 1;\n}\n"
      : "+f"(d[0]), "+f"(d[1]), "+f"(d[2]), "+f"(d[3]), "+f"(d[4]), "+f"(d[5]), "+f"(d[6]), "+f"(d[7]),
        "+f"(d[8]), "+f"(d[9]), "+f"(d[10]), "+f"(d[11]), "+f"(d[12]), "+f"(d[13]), "+f"(d[14]), "+f"(d[15]),
        "+f"(d[16]), "+f"(d[17]), "+f"(d[18]), "+f"(d[19]), "+f"(d[20]), "+f"(d[21]), "+f"(d[22]), "+f"(d[23]),
        "+f"(d[24]), "+f"(d[25]), "+f"(d[26]), "+f"(d[27]), "+f"(d[28]), "+f"(d[29]), "+f"(d[30]), "+f"(d[31]),
        "+f"(d[32]), "+f"(d[33]), "+f"(d[34]), "+f"(d[35]), "+f"(d[36]), "+f"(d[37]), "+f"(d[38]), "+f"(d[39])
      : "r"(da), "n"(HA), "r"(db), "n"(HB), "r"(sc));
  }
};
template <> struct WgSST<192> {
  template <uint32_t HA, uint32_t HB>
  static __device__ __forceinline__ void mma(float* d, uint32_t da, uint32_t db, int sc) {
    asm volatile("{\n.reg .pred p;\n.reg .b64 da, db;\nsetp.ne.b32 p, %100, 0;\n"
      "mov.b64 da, {%96, %97};\nmov.b64 db, {%98, %99};\n"
      "wgmma.mma_async.sync.aligned.m64n192k16.f32.bf16.bf16 {"
      "%0, %1, %2, %3, %4, %5, %6, %7, %8, %9, %10, %11, %12, %13, %14, %15, "
      "%16, %17, %18, %19, %20, %21, %22, %23, %24, %25, %26, %27, %28, %29, %30, %31, "
      "%32, %33, %34, %35, %36, %37, %38, %39, %40, %41, %42, %43, %44, %45, %46, %47, "
      "%48, %49, %50, %51, %52, %53, %54, %55, %56, %57, %58, %59, %60, %61, %62, %63, "
      "%64, %65, %66, %67, %68, %69, %70, %71, %72, %73, %74, %75, %76, %77, %78, %79, "
      "%80, %81, %82, %83, %84, %85, %86, %87, %88, %89, %90, %91, %92, %93, %94, %95"
      "}, da, db, p, 1, 1, 0, 1;\n}\n"
      : "+f"(d[0]), "+f"(d[1]), "+f"(d[2]), "+f"(d[3]), "+f"(d[4]), "+f"(d[5]), "+f"(d[6]), "+f"(d[7]),
        "+f"(d[8]), "+f"(d[9]), "+f"(d[10]), "+f"(d[11]), "+f"(d[12]), "+f"(d[13]), "+f"(d[14]), "+f"(d[15]),
        "+f"(d[16]), "+f"(d[17]), "+f"(d[18]), "+f"(d[19]), "+f"(d[20]), "+f"(d[21]), "+f"(d[22]), "+f"(d[23]),
        "+f"(d[24]), "+f"(d[25]), "+f"(d[26]), "+f"(d[27]), "+f"(d[28]), "+f"(d[29]), "+f"(d[30]), "+f"(d[31]),
        "+f"(d[32]), "+f"(d[33]), "+f"(d[34]), "+f"(d[35]), "+f"(d[36]), "+f"(d[37]), "+f"(d[38]), "+f"(d[39]),
        "+f"(d[40]), "+f"(d[41]), "+f"(d[42]), "+f"(d[43]), "+f"(d[44]), "+f"(d[45]), "+f"(d[46]), "+f"(d[47]),
        "+f"(d[48]), "+f"(d[49]), "+f"(d[50]), "+f"(d[51]), "+f"(d[52]), "+f"(d[53]), "+f"(d[54]), "+f"(d[55]),
        "+f"(d[56]), "+f"(d[57]), "+f"(d[58]), "+f"(d[59]), "+f"(d[60]), "+f"(d[61]), "+f"(d[62]), "+f"(d[63]),
        "+f"(d[64]), "+f"(d[65]), "+f"(d[66]), "+f"(d[67]), "+f"(d[68]), "+f"(d[69]), "+f"(d[70]), "+f"(d[71]),
        "+f"(d[72]), "+f"(d[73]), "+f"(d[74]), "+f"(d[75]), "+f"(d[76]), "+f"(d[77]), "+f"(d[78]), "+f"(d[79]),
        "+f"(d[80]), "+f"(d[81]), "+f"(d[82]), "+f"(d[83]), "+f"(d[84]), "+f"(d[85]), "+f"(d[86]), "+f"(d[87]),
        "+f"(d[88]), "+f"(d[89]), "+f"(d[90]), "+f"(d[91]), "+f"(d[92]), "+f"(d[93]), "+f"(d[94]), "+f"(d[95])
      : "r"(da), "n"(HA), "r"(db), "n"(HB), "r"(sc));
  }
};

struct FftConst {
  uint32_t f[2][4], fi[4][4];
  float ta[4], tb[4];
};
__device__ __forceinline__ void cis(int m, float scale, float& c, float& s) {
  const float a = (float)m * (-6.283185307179586f * scale);
  c = __cosf(a);
  s = __sinf(a);
}
__device__ __forceinline__ void fft_tables(uint32_t (&v)[12], int tw) {
  const int row = tw >> 2, ch = tw & 3;
#pragma unroll
  for (int i = 0; i < 4; i++) {
    float c[2], s[2], x[2];
#pragma unroll
    for (int e = 0; e < 2; e++) {
      cis((((32 * (8 * ch + 2 * i + e) + 15) * (4 * row - 63) + 2048) & 4095) - 2048, 1.f / 4096, c[e], s[e]);
      float gc, gs;
      cis((((row & 15) * (8 * (ch & 1) + 2 * i + e) + 8) & 15) - 8, 1.f / 16, gc, gs);
      x[e] = (row >> 4) == (ch >> 1) ? gc : (ch >> 1) ? gs : -gs;
    }
    v[i] = pack2(c[0] * 0.125f, c[1] * 0.125f);
    v[4 + i] = pack2(s[0] * 0.125f, s[1] * 0.125f);
    v[8 + i] = pack2(x[0], x[1]);
  }
#pragma unroll
  for (int i = 0; i < 12; i++) asm volatile("" : "+r"(v[i]));
}
__device__ __forceinline__ void fft_tables_store(const uint32_t (&v)[12], uint32_t sb, int tw) {
  const int row = tw >> 2;
  const uint32_t x = ((tw ^ (row >> 1)) & 3) << 4, a = sb + OFF_FT + (16 * (row >> 3) + (row & 7)) * 64 + x;
  sts128(a, v[0], v[1], v[2], v[3]);
  sts128(a + 512, v[4], v[5], v[6], v[7]);
  sts128(sb + OFF_GT + row * 64 + x, v[8], v[9], v[10], v[11]);
}
__device__ __forceinline__ void fft_twiddles(FftConst& k, int w, int lane) {
#pragma unroll
  for (int i = 0; i < 4; i++) {
    float c, s;
    cis((2 * (8 * (i >> 1) + 2 * (lane & 3) + (i & 1)) - 15) * (4 * (8 * w + (lane >> 2)) - 63), 1.f / 4096, c, s);
    k.ta[i] = __fdividef(-s, 1.f + c);
    k.tb[i] = s;
  }
  pin<4>(k.ta);
  pin<4>(k.tb);
}
__device__ __forceinline__ void fft_matrices(FftConst& k, uint32_t sb, int w, int lane) {
  const uint32_t x = (lane >> 1) & 3;
#pragma unroll
  for (int i = 0; i < 2; i++) {
    ldsm4(k.f[i], sb + OFF_FT + (16 * w + (lane & 15)) * 64 + (((2 * i + (lane >> 4)) ^ x) << 4));
    ldsm4t(k.fi[i], sb + OFF_FT + (32 * i + lane) * 64 + ((w ^ x) << 4));
#pragma unroll
    for (int j = 0; j < 4; j++) {
      k.fi[2 + i][j] = (j & 1) ? k.fi[i][j - 1] ^ 0x80008000u : k.fi[i][j + 1];
      asm volatile("" : "+r"(k.fi[2 + i][j]));
    }
  }
}
template <bool INV> __device__ __forceinline__ void rot(float& x, float& y, float a, float b) {
  x = fmaf(INV ? -a : a, y, x);
  y = fmaf(INV ? -b : b, x, y);
  x = fmaf(INV ? -a : a, y, x);
}
__device__ __forceinline__ void twiddle_fwd(uint32_t (&a)[4][4], float* d, const FftConst& k) {
#pragma unroll
  for (int q = 0; q < 4; q++)
#pragma unroll
    for (int j = 0; j < 2; j++) {
      float* x = d + 8 * q + 4 * j;
      rot<false>(x[0], x[2], k.ta[2 * j], k.tb[2 * j]);
      rot<false>(x[1], x[3], k.ta[2 * j + 1], k.tb[2 * j + 1]);
      a[q & 2][2 * j + (q & 1)] = pack2(x[0], x[1]);
      a[(q & 2) + 1][2 * j + (q & 1)] = pack2(x[2], x[3]);
    }
}
__device__ __forceinline__ void g_step(float* d, const uint32_t (&a)[4][4], uint32_t dre, uint32_t dim) {
  WgRS<32>::set<HI_SW64>(d, a[0], dre);
  WgRS<32>::set<HI_SW64>(d + 16, a[2], dre);
  WgRS<32>::mma<HI_SW64>(d, a[1], dim);
  WgRS<32>::mma<HI_SW64>(d + 16, a[3], dim);
  wg_commit();
}

__device__ __forceinline__ void conv_channel(const FftConst& k, uint32_t sb, int c, int wg, int w, int lane) {
  const uint32_t cb = sb + off_ch(c), bars = sb + OFF_BAR;
  const uint32_t du = desc_lo(cb, 1024), dg = desc_lo(sb + OFF_GT, 16), dz = desc_lo(cb + U_BYTES, 16);
  float U[32], H[32];
  uint32_t a[4][4], e[4][4];
  const float dv = __uint_as_float(lds32(sb + OFF_D + 4 * c));
  wg_fence();
  WgRS<64>::set<HI_SW32>(H, k.f[0], du + 256);
  WgRS<64>::mma<HI_SW32>(H, k.f[1], du + 256 + 32);
  wg_commit();
  wg_wait<0>();
  pin<32>(H);
  twiddle_fwd(a, H, k);
  if (ATT_GATE && H_EARLY) mbar_wait(bars + 8 * B_ATTN, 0);
  mbar_wait(bars + 8 * (B_U + (c < 3 ? c : 3)), 0);
  TSM(w == 0 && c < 3, 7 + wg);
  if (TOK_G < 8 && c > 0) mbar_wait(bars + 8 * (B_TOK + c - 1), 0);
  wg_fence();
  WgRS<64>::set<HI_SW32>(U, k.f[0], du);
  WgRS<64>::mma<HI_SW32>(U, k.f[1], du + 32);
  wg_commit();
  g_step(H, a, dg, dg + 64);
  wg_wait<1>();
  pin<32>(U);
  if (TOK_G == 1 && lane == 0) mbar_arrive(bars + 8 * (B_TOK + c));
  twiddle_fwd(e, U, k);
  wg_fence();
  g_step(U, e, dg, dg + 64);
  if (TOK_G == 2 && lane == 0) mbar_arrive(bars + 8 * (B_TOK + c));
  wg_wait<0>();
  pin<32>(U);
  pin<32>(H);
#pragma unroll
  for (int j = 0; j < 2; j++) {
    float pr[4][2], pi[4][2];
#pragma unroll
    for (int x = 0; x < 2; x++) {
      H[4 * j + x] += dv;
#pragma unroll
      for (int m = 0; m < 4; m++) {
#pragma unroll
        for (int q = 0; q <= m; q++) {
          const int ih = 16 * (q >> 1) + 2 * (q & 1) + 4 * j + x, iu = 16 * ((m - q) >> 1) + 2 * ((m - q) & 1) + 4 * j + x;
          pr[m][x] = q ? fmaf(H[ih], U[iu], pr[m][x]) : H[ih] * U[iu];
          pi[m][x] = q ? fmaf(H[ih], U[iu + 8], pi[m][x]) : H[ih] * U[iu + 8];
          pr[m][x] = fmaf(-H[ih + 8], U[iu + 8], pr[m][x]);
          pi[m][x] = fmaf(H[ih + 8], U[iu], pi[m][x]);
        }
      }
    }
#pragma unroll
    for (int m = 0; m < 4; m++) {
      a[m & 2][2 * j + (m & 1)] = pack2(pr[m][0], pr[m][1]);
      a[(m & 2) + 1][2 * j + (m & 1)] = pack2(pi[m][0], pi[m][1]);
    }
  }
  wg_fence();
  g_step(U, a, dg + 64, dg);
  if (TOK_G == 3 && lane == 0) mbar_arrive(bars + 8 * (B_TOK + c));
  const uint32_t za = cb + U_BYTES + (8 * w + (lane & 7)) * 128 + (((lane >> 3) ^ (lane & 7)) << 4);
  const uint32_t ya = cb + (lane >> 4) * 1024 + (8 * w + (lane & 7)) * 32 + ((((lane >> 3) ^ (lane >> 2)) & 1) << 4);
  wg_sync(1 + wg);
  wg_wait<0>();
  pin<32>(U);
  TSIF(w == 0, 80 + c);
#pragma unroll
  for (int p = 0; p < 2; p++) {
#pragma unroll
    for (int i = 0; i < 4; i++) {
      const int j = i & 1;
      float* x = U + 16 * p + 4 * j + (i & 2);
      rot<true>(x[8], x[0], k.ta[2 * j], k.tb[2 * j]);
      rot<true>(x[9], x[1], k.ta[2 * j + 1], k.tb[2 * j + 1]);
      e[p][i] = pack2(x[8], x[9]);
      e[2 + p][i] = pack2(x[0], x[1]);
    }
    stsm4(za ^ (64 * p), e[p]);
    stsm4((za ^ (64 * p)) + 4096, e[2 + p]);
  }
  fence_async_smem();
  wg_sync(1 + wg);
  wg_fence();
  WgRS<64>::set<HI_SW128>(H, k.fi[0], dz);
#pragma unroll
  for (int ks = 1; ks < 4; ks++) WgRS<64>::mma<HI_SW128>(H, k.fi[ks], dz + 128 * ks);
  wg_commit();
  wg_wait<0>();
  pin<32>(H);
  TSIF(w == 0, 88 + c);
#pragma unroll
  for (int j = 0; j < 8; j++)
    a[j >> 2][j & 3] = j < 2 ? pack2(H[4 * j], H[4 * j + 1]) : pack2(H[4 * j] + H[4 * j - 6], H[4 * j + 1] + H[4 * j - 5]);
  stsm4(ya, a[0]);
  stsm4(ya + 2048, a[1]);
  fence_async_smem();
  __syncwarp();
}

__device__ __forceinline__ void prep_slab(uint4* res, const uint2* sw, uint32_t sb, int slab, int w, int lane) {
  const int t = lane & 3, tp = (lane & 7) >> 1, pos = 8 * tp + 2 * (((lane >> 3) + tp) & 3) + (lane & 1);
  const uint32_t base = sb + OFF_KVS + slab * KVS_BYTES + pos * 128;
  uint32_t kk[2][4][4], vv[2][4];
  mbar_wait(sb + OFF_BAR + 8 * (B_KV + slab), 0);
#pragma unroll
  for (int h = 0; h < 2; h++) {
#pragma unroll
    for (int j = 0; j < 4; j++) {
      const uint32_t a = base + 128 * j;
      ldsm4t(kk[h][j], a + (((w + 4 * h) ^ ((a >> 7) & 7)) << 4));
    }
    const uint32_t a = base + KVS_V;
    ldsm4t(vv[h], a + (((w + 4 * h) ^ ((a >> 7) & 7)) << 4));
  }
#pragma unroll
  for (int h = 0; h < 2; h++) {
    uint32_t (&k)[4][4] = kk[h];
    uint32_t (&v)[4] = vv[h];
    const uint32_t w0 = __byte_perm(sw[h].x, 0, 0x1010), w1 = __byte_perm(sw[h].x, 0, 0x3232);
    const uint32_t w2 = __byte_perm(sw[h].y, 0, 0x1010), w3 = __byte_perm(sw[h].y, 0, 0x3232);
#pragma unroll
    for (int m = 0; m < 4; m++)
      v[m] = bmul(badd(badd(badd(bmul(k[0][m], w3), bmul(k[1][m], w2)), bmul(k[2][m], w1)), bmul(k[3][m], w0)), v[m]);
    uint32_t a[4];
#pragma unroll
    for (int m = 0; m < 4; m++) a[m] = (t & 1) ? v[(m + 3) & 3] : v[m];
    res[h] = (t & 2) ? make_uint4(a[2], a[3], a[0], a[1]) : make_uint4(a[0], a[1], a[2], a[3]);
  }
}

__device__ __forceinline__ void prep_gate(const Params& p, int b, int w, int lane) {
  uint2 gw[5], x[4][5];
#pragma unroll
  for (int j = 0; j < 5; j++) gw[j] = ldg64(reinterpret_cast<const uint2*>(p.gate_w) + lane + 32 * j);
#pragma unroll
  for (int i = 0; i < 4; i++)
#pragma unroll
    for (int j = 0; j < 5; j++)
      x[i][j] = ldg64(reinterpret_cast<const uint2*>(p.q) + (16 * b + 4 * w + i) * (DIM / 4) + lane + 32 * j);
  float s[4];
#pragma unroll
  for (int i = 0; i < 4; i++) {
    s[i] = 0.f;
#pragma unroll
    for (int j = 0; j < 5; j++) {
      const uint32_t m0 = bmul(x[i][j].x, gw[j].x), m1 = bmul(x[i][j].y, gw[j].y);
      s[i] += (bf_lo(m0) + bf_hi(m0)) + (bf_lo(m1) + bf_hi(m1));
    }
  }
  const bool h = lane & 16, q = lane & 8;
  const float a = (h ? s[2] : s[0]) + __shfl_xor_sync(0xffffffffu, h ? s[0] : s[2], 16);
  const float c = (h ? s[3] : s[1]) + __shfl_xor_sync(0xffffffffu, h ? s[1] : s[3], 16);
  float z = (q ? c : a) + __shfl_xor_sync(0xffffffffu, q ? a : c, 8);
#pragma unroll
  for (int o = 4; o > 0; o >>= 1) z += __shfl_xor_sync(0xffffffffu, z, o);
  z = bf_lo(pack2(z, 0.f));
  if ((lane & 7) == 0) g_gate[16 * b + 4 * w + (lane >> 3)] = bf_lo(pack2(__fdividef(1.f, 1.f + __expf(-z)), 0.f));
}

__device__ __forceinline__ uint32_t bmax(uint32_t a, uint32_t b) {
  uint32_t d;
  asm("max.bf16x2 %0, %1, %2;" : "=r"(d) : "r"(a), "r"(b));
  return d;
}
__device__ __forceinline__ void softmax_two(const float (&l)[2][2], uint32_t& p0, uint32_t& p1) {
  constexpr float kScale = 0.22360679774997896f, kLog2e = 1.4426950408889634f;
  const uint32_t r0 = pack2(l[0][0], l[1][0]), r1 = pack2(l[0][1], l[1][1]);
  const uint32_t x0 = pack2(bf_lo(r0) * kScale, bf_hi(r0) * kScale), x1 = pack2(bf_lo(r1) * kScale, bf_hi(r1) * kScale);
  uint32_t m = bmax(x0, x1);
  m = bmax(m, __shfl_xor_sync(0xffffffffu, m, 1));
  m = bmax(m, __shfl_xor_sync(0xffffffffu, m, 2));
  const float m0 = bf_lo(m) * kLog2e, m1 = bf_hi(m) * kLog2e;
  p0 = pack2(ex2(bf_lo(x0) * kLog2e - m0), ex2(bf_lo(x1) * kLog2e - m0));
  p1 = pack2(ex2(bf_hi(x0) * kLog2e - m1), ex2(bf_hi(x1) * kLog2e - m1));
}

__device__ __forceinline__ void halo_read(uint32_t (&kpv)[10], uint32_t (&vpv)[10], uint32_t (&tg)[7], const uint4* hp) {
#pragma unroll
  for (int j = 0; j < 7; j++) {
    uint32_t x0, x1, x2;
    asm volatile("ld.relaxed.gpu.global.v4.u32 {%0, %1, %2, %3}, [%4];"
                 : "=r"(x0), "=r"(x1), "=r"(x2), "=r"(tg[j]) : "l"(hp + 32 * j) : "memory");
    if (j < 4) kpv[3 * j] = x0; else vpv[3 * j - 10] = x0;
    if (j < 3) kpv[3 * j + 1] = x1; else vpv[3 * j - 9] = x1;
    if (j < 3) kpv[3 * j + 2] = x2; else if (j < 6) vpv[3 * j - 8] = x2;
  }
}

template <int ROT>
__device__ __forceinline__ void pack_qkv(const float* acc, uint32_t (&qlo)[10], uint32_t (&qhi)[10], uint32_t (&klo)[10],
                                         uint32_t (&khi)[10], uint32_t (&vlo)[10], uint32_t (&vhi)[10]) {
#pragma unroll
  for (int j = 0; j < 10; j++) {
    const int x = (j + ROT) % 10, tq = x < 8 ? x : 16 + x, tk = x < 8 ? 8 + x : 18 + x, tv = x < 8 ? 16 + x : 20 + x;
    khi[j] = pack2(acc[4 * tk + 2], acc[4 * tk + 3]);
    vhi[j] = movm(pack2(acc[4 * tv + 2], acc[4 * tv + 3]));
    qlo[j] = pack2(acc[4 * tq], acc[4 * tq + 1]);
    qhi[j] = pack2(acc[4 * tq + 2], acc[4 * tq + 3]);
    klo[j] = pack2(acc[4 * tk], acc[4 * tk + 1]);
    vlo[j] = pack2(acc[4 * tv], acc[4 * tv + 1]);
    asm volatile("" : "+r"(khi[j]), "+r"(qlo[j]), "+r"(qhi[j]), "+r"(klo[j]), "+r"(vlo[j]));
  }
}

__device__ __forceinline__ void attention(float* acc, uint32_t sb, int b, int par, int w, int lane) {
  const int g = lane >> 2, t = lane & 3;
  uint32_t klo[10], khi[10], vlo[10], vhi[10], qlo[10], qhi[10], kpv[10], vpv[10];
  if (tail_first(b & 7)) pack_qkv<8>(acc, qlo, qhi, klo, khi, vlo, vhi);
  else pack_qkv<0>(acc, qlo, qhi, klo, khi, vlo, vhi);
  uint32_t tag = 0;
  if (w == 0 || w == 3) {
    mbar_wait(sb + OFF_BAR + 8 * B_EPOCH, 0);
    tag = lds32(sb + OFF_EPOCH) + 1;
  }
  const uint32_t xa = sb + OFF_KVX + (par * 3) * 2560 + lane * 16;
  if (w < 3) {
    mbar_wait(sb + OFF_BAR + 8 * B_S3, 0);
    sts128(xa + w * 2560, khi[0], khi[1], khi[2], khi[3]);
    sts128(xa + w * 2560 + 512, khi[4], khi[5], khi[6], khi[7]);
    sts128(xa + w * 2560 + 1024, khi[8], khi[9], vhi[0], vhi[1]);
    sts128(xa + w * 2560 + 1536, vhi[2], vhi[3], vhi[4], vhi[5]);
    sts128(xa + w * 2560 + 2048, vhi[6], vhi[7], vhi[8], vhi[9]);
  } else if (b < NCTA - 8) {
    uint4* ho = g_halo + (b * 2 + par) * 224 + lane;
#pragma unroll
    for (int j = 0; j < 7; j++) {
      const uint32_t x0 = j < 4 ? khi[3 * j] : vhi[3 * j - 10], x1 = j < 3 ? khi[3 * j + 1] : vhi[3 * j - 9];
      const uint32_t x2 = j < 3 ? khi[3 * j + 2] : j < 6 ? vhi[3 * j - 8] : 0u;
      asm volatile("st.relaxed.gpu.global.v4.u32 [%0], {%1, %2, %3, %4};" ::"l"(ho + 32 * j), "r"(x0), "r"(x1), "r"(x2), "r"(tag) : "memory");
    }
  }
  TSIF(par == 0 && w == 1, 64);
  TSIF(par == 0 && w == 3, 76);
#pragma unroll
  for (int j = 0; j < 10; j++) vlo[j] = movm(vlo[j]);
  const bool far0 = 2 * t > g, far1 = 2 * t + 1 > g;
  const uint32_t mfar = (far0 ? 0x0000FFFFu : 0u) | (far1 ? 0xFFFF0000u : 0u);
  float slo[4][2], shi[4][2], lg[2][2];
  uint32_t phi[4], plo[4], qml[4], qmh[4];
#pragma unroll
  for (int h = 0; h < 4; h++) {
    const int f = h == 0 ? 0 : h == 1 ? 3 : h == 2 ? 5 : 8, hf = h < 2 ? 2 : 7;
    const bool mine = (h & 1) ? t >= 2 : t < 2;
    qml[h] = mine ? qlo[hf] : 0u;
    qmh[h] = mine ? qhi[hf] : 0u;
    float a[4] = {0.f, 0.f, 0.f, 0.f}, c[4] = {0.f, 0.f, 0.f, 0.f};
    mma16816(a, qlo[f], qhi[f], qlo[f + 1], qhi[f + 1], klo[f], klo[f + 1]);
    mma16816(c, qlo[f], qhi[f], qlo[f + 1], qhi[f + 1], khi[f], khi[f + 1]);
    mma1688(a, qml[h], qmh[h], klo[hf]);
    mma1688(c, qml[h], qmh[h], khi[hf]);
    slo[h][0] = a[0];
    slo[h][1] = a[1];
    shi[h][0] = lg[h & 1][0] = far0 ? a[2] : c[2];
    shi[h][1] = lg[h & 1][1] = far1 ? a[3] : c[3];
    if (!ATT_MERGE && (h & 1)) softmax_two(lg, phi[h - 1], phi[h]);
  }
  TSIF(par == 0 && w == 1, 65);
  wg_sync(1 + par);
  TSIF(par == 0 && w == 1, 66);
  const bool nohist = (w == 0) && (b < 8);
  const uint4* hp = g_halo + ((b - 8) * 2 + par) * 224 + lane;
  uint32_t tg[7];
  if (w > 0) {
    const uint4 v0 = lds128(xa + (w - 1) * 2560), v1 = lds128(xa + (w - 1) * 2560 + 512), v2 = lds128(xa + (w - 1) * 2560 + 1024);
    const uint4 v3 = lds128(xa + (w - 1) * 2560 + 1536), v4 = lds128(xa + (w - 1) * 2560 + 2048);
    kpv[0] = v0.x; kpv[1] = v0.y; kpv[2] = v0.z; kpv[3] = v0.w; kpv[4] = v1.x; kpv[5] = v1.y; kpv[6] = v1.z; kpv[7] = v1.w;
    kpv[8] = v2.x; kpv[9] = v2.y; vpv[0] = v2.z; vpv[1] = v2.w; vpv[2] = v3.x; vpv[3] = v3.y; vpv[4] = v3.z; vpv[5] = v3.w;
    vpv[6] = v4.x; vpv[7] = v4.y; vpv[8] = v4.z; vpv[9] = v4.w;
  } else if (nohist) {
#pragma unroll
    for (int j = 0; j < 10; j++) kpv[j] = vpv[j] = 0u;
  } else {
    TSIF(par == 0, 77);
    halo_read(kpv, vpv, tg, hp);
  }
  if (w == 0 && !nohist) {
    int spins = 0;
    while (true) {
      bool ok = true;
#pragma unroll
      for (int j = 0; j < 7; j++) ok = ok && tg[j] == tag;
      if (__all_sync(0xffffffffu, ok) || ++spins > SPIN_LIMIT) break;
      halo_read(kpv, vpv, tg, hp);
    }
    TSIF(par == 0, 79);
  }
#pragma unroll
  for (int h = 0; h < 4; h++) {
    const int f = h == 0 ? 0 : h == 1 ? 3 : h == 2 ? 5 : 8, hf = h < 2 ? 2 : 7;
    float a[4] = {0.f, 0.f, 0.f, 0.f};
    mma16816(a, qlo[f], qhi[f], qlo[f + 1], qhi[f + 1], kpv[f], kpv[f + 1]);
    mma1688(a, qml[h], qmh[h], kpv[hf]);
    const float ninf = __int_as_float(0xff800000);
    lg[h & 1][0] = far0 ? (nohist ? ninf : a[0]) : slo[h][0];
    lg[h & 1][1] = far1 ? (nohist ? ninf : a[1]) : slo[h][1];
    if (h & 1) {
      softmax_two(lg, plo[h - 1], plo[h]);
      if (ATT_MERGE) {
        const float lh[2][2] = {{shi[h - 1][0], shi[h - 1][1]}, {shi[h][0], shi[h][1]}};
        softmax_two(lh, phi[h - 1], phi[h]);
      }
    }
  }
  TSIF(par == 0 && w <= 1, 67 + w);
  uint32_t ov[20];
#pragma unroll
  for (int hp = 0; hp < 2; hp++) {
    const int hf = hp ? 7 : 2;
    float sh[4] = {0.f, 0.f, 0.f, 0.f}, i0 = 0.f, i1 = 0.f;
#pragma unroll
    for (int e = 0; e < 2; e++) {
      const int h = 2 * hp + e, f = h == 0 ? 0 : h == 1 ? 3 : h == 2 ? 5 : 8;
      const uint32_t a0 = plo[h] & mfar, a2 = plo[h] & ~mfar, a3 = phi[h] & mfar, c1 = phi[h] & ~mfar;
      float sum[4] = {0.f, 0.f, 0.f, 0.f};
      mma1688(sum, plo[h], phi[h], 0x3F803F80u);
      const float r0 = rcp(sum[0]), r1 = rcp(sum[2]);
#pragma unroll
      for (int j = f; j < f + 2; j++) {
        float o[4] = {0.f, 0.f, 0.f, 0.f};
        mma16816(o, a0, 0u, a2, a3, vpv[j], vlo[j]);
        mma1688(o, 0u, c1, vhi[j]);
        ov[2 * j] = pack2(o[0] * r0, o[1] * r0);
        ov[2 * j + 1] = pack2(o[2] * r1, o[3] * r1);
      }
      const bool mine = e ? g >= 4 : g < 4;
      mma16816(sh, a0, 0u, a2, a3, mine ? vpv[hf] : 0u, mine ? vlo[hf] : 0u);
      mma1688(sh, 0u, c1, mine ? vhi[hf] : 0u);
      if (e == 0 || t >= 2) {
        i0 = r0;
        i1 = r1;
      }
    }
    ov[2 * hf] = pack2(sh[0] * i0, sh[1] * i0);
    ov[2 * hf + 1] = pack2(sh[2] * i1, sh[3] * i1);
  }
  TS(32 + 4 * par + w);
  mbar_wait(sb + OFF_BAR + 8 * B_P1, 0);
  const uint32_t oa = sb + OFF_OA + (lane >> 4) * 2048 + (32 * w + 2 * (lane & 15) + par) * 16;
#pragma unroll
  for (int j = 0; j < 5; j++) stsm4(oa + 4096 * j, ov + 4 * j);
  TSIF(par == 0 && w == 0, 120);
  fence_async_smem();
  TSIF(par == 0 && w == 0, 121);
  __syncwarp();
  if (lane == 0) mbar_arrive(sb + OFF_BAR + 8 * B_ATTN);
  TSIF(par == 0 && w == 0, 122);
}

struct Maps {
  CUtensorMap x, wm, wt, k, v, y, wo, qm, qt, om, ot;
};

__device__ __forceinline__ void load_stage(uint32_t sb, int kb, int b, const Maps& m) {
  const uint32_t st = sb + (kb & 3) * STAGE_BYTES, bar = sb + OFF_BAR + 8 * (B_FULL1 + (kb & 3));
  const int r = b >> 3, hg = b & 7, slab = kb - KV_KB;
  const bool kv = slab >= 0 && slab < 5;
  const uint32_t kbar = sb + OFF_BAR + 8 * (B_KV + slab), dst = sb + OFF_KVS + slab * KVS_BYTES;
  mbar_expect_tx(bar, STAGE_BYTES);
  if (kv) mbar_expect_tx(kbar, KVS_BYTES);
  tma_3d(st, &m.x, 64 * kb, 64 * r, 0, bar);
  if (kv && KV_MIX) tma_3d(dst, &m.k, 0, 32 * (b >> 1) - 3, 2 * slab + (b & 1), kbar);
  tma_3d(st + ST_W, &m.wm, 80 * hg + (tail_first(hg) ? 16 : 0), 64 * kb, 0, bar);
  if (kv && KV_MIX) tma_3d(dst + KVS_V, &m.v, 0, 32 * (b >> 1), 2 * slab + (b & 1), kbar);
  tma_3d(st + ST_WT, &m.wt, 80 * hg + (tail_first(hg) ? 0 : 64), 64 * kb, 0, bar);
  if (kv && !KV_MIX) tma_3d(dst, &m.k, 0, 32 * (b >> 1) - 3, 2 * slab + (b & 1), kbar);
  if (kv && !KV_MIX) tma_3d(dst + KVS_V, &m.v, 0, 32 * (b >> 1), 2 * slab + (b & 1), kbar);
}

__global__ void __launch_bounds__(NTHR, 1) fused_kernel(const __grid_constant__ Maps m, const Params p) {
  extern __shared__ __align__(1024) uint8_t smem[];
  const uint32_t sb = (uint32_t)__cvta_generic_to_shared(smem);
  const uint32_t bars = sb + OFF_BAR;
  const int tid = threadIdx.x, lane = tid & 31;
  int b = blockIdx.x;
  if (BMAP == 1) b = (((b & 63) >> 3) * 2 + (b & 1)) * 8 + (((b < 64 ? 0x6521 : 0x7430) >> (4 * ((b >> 1) & 3))) & 7);
  if (BMAP == 2) b = ((b & 63) >> 2) * 8 + (((b < 64 ? 0x6521 : 0x7430) >> (4 * (b & 3))) & 7);
  if (BMAP == 3) b = (((b & 63) >> 3) * 2 + (b & 1)) * 8 + (((b < 64 ? 0x7430 : 0x6521) >> (4 * ((b >> 1) & 3))) & 7);
  if (BMAP == 4) b = (((b >> 4) * 2 + (b & 1)) * 8) + ((b >> 1) & 7);
  if (BMAP == 5) b = 127 - b;
  const int r = b >> 3, hg = b & 7;

  if (tid == T_ISSUE) {
    TSM(true, 0);
#pragma unroll
    for (int i = 0; i < 4; i++) mbar_init(bars + 8 * (B_FULL1 + i), 1);
#pragma unroll
    for (int i = 0; i < 3; i++) mbar_init(bars + 8 * (B_KV + i), 1);
    fence_async_smem();
#pragma unroll 1
    for (int kb = 0; kb <= PRE2; kb++) load_stage(sb, kb, b, m);
  } else if (tid >= T_PF && tid < T_PF + 11) {
    tm_prefetch(&m.x + (tid - T_PF));
  } else if (tid == T_INIT) {
#pragma unroll
    for (int i = 0; i < 4; i++) mbar_init(bars + 8 * (B_EMPTY1 + i), 8);
#pragma unroll
    for (int i = 0; i < 8; i++) mbar_init(bars + 8 * (B_FULL2 + i), 1);
#pragma unroll
    for (int i = 0; i < 4; i++) mbar_init(bars + 8 * (B_EMPTY2 + i), 8);
#pragma unroll
    for (int i = 0; i < 4; i++) mbar_init(bars + 8 * (B_U + i), 1);
    mbar_init(bars + 8 * B_HA, 4);
    mbar_init(bars + 8 * B_GATE, 4);
    mbar_init(bars + 8 * B_HB, 1);
    mbar_init(bars + 8 * B_KVD, 4);
    mbar_init(bars + 8 * B_QF, 1);
    mbar_init(bars + 8 * B_ATTN, 8);
    mbar_init(bars + 8 * B_P1, 8);
    mbar_init(bars + 8 * B_C34, 1);
#pragma unroll
    for (int i = 0; i < 5; i++) mbar_init(bars + 8 * (B_YST + i), 4);
#pragma unroll
    for (int i = 0; i < 5; i++) mbar_init(bars + 8 * (B_TOK + i), 4);
    mbar_init(bars + 8 * B_YSIG, 1);
    mbar_init(bars + 8 * B_YFULL, 1);
    mbar_init(bars + 8 * B_EPOCH, 1);
    mbar_init(bars + 8 * B_PREP, 4);
    mbar_init(bars + 8 * B_USIG, 1);
    mbar_init(bars + 8 * B_WST, 1);
#pragma unroll
    for (int i = 3; i < 5; i++) mbar_init(bars + 8 * (B_KV + i), 1);
    mbar_init(bars + 8 * B_E3, 8);
    mbar_init(bars + 8 * B_LAST, 1);
    mbar_init(bars + 8 * B_OSIG, 1);
    mbar_init(bars + 8 * B_WOP, 1);
    fence_async_smem();
  }
  const int warp = __shfl_sync(0xffffffffu, tid >> 5, 0), wg = warp >> 2, w = warp & 3;
  __syncthreads();

  if (wg == 3) {
    asm volatile("setmaxnreg.dec.sync.aligned.u32 56;");
    if (w == 0) {
      if (lane == 0) {
#pragma unroll 1
        for (int kb = 1 + PRE2; kb < 10; kb++) {
          if (kb >= 4) mbar_wait(bars + 8 * (kb == 7 ? B_E3 : B_EMPTY1 + (kb & 3)), (kb >> 3) & 1);
          TSIF(kb >= 4, 44 + kb);
          if (WO_EARLY && kb == KV_KB + 4) mbar_wait(bars + 8 * B_WOP, 0);
          load_stage(sb, kb, b, m);
          if (kb == TRIG_KB) mbar_arrive(bars + 8 * B_LAST);
          if (WO_EARLY && kb == WO_EARLY) {
            mbar_expect_tx(bars + 8 * B_WST, WO_BYTES / 2);
            tma_3d(sb + OFF_WS, &m.wo, 0, 40 * r, 5 * hg, bars + 8 * B_WST);
          }
        }
        mbar_wait(bars + 8 * B_P1, 0);
        mbar_wait(bars + 8 * WL_TRIG, 0);
        mbar_wait(bars + 8 * B_EPOCH, 0);
        flag_wait(g_cnt + C_W + 32 * hg, (lds32(sb + OFF_EPOCH) + 1) * 16);
        TS(30);
#pragma unroll 1
        for (int j = 0; j < 8; j++) {
          if (j >= 6) mbar_wait(bars + 8 * (B_EMPTY2 + j - 6), 0);
          if (j == 4) mbar_wait(bars + 8 * B_ATTN, 0);
          TSIF(j >= 6, 100 + j);
          if (RF_GATE && j == 6) mbar_wait(bars + 8 * B_YSIG, 0);
          mbar_expect_tx(bars + 8 * (B_FULL2 + j), j == 0 ? WO_BYTES : j == 5 ? O_BYTES + WO_BYTES + 512 : O_BYTES + WO_BYTES);
          bulk_load(sb + off_w(j), g_WO + (hg * 8 + step_src(hg, j)) * 800, WO_BYTES, bars + 8 * (B_FULL2 + j));
        }
        mbar_wait(bars + 8 * (B_EMPTY2 + 3), 0);
        mbar_expect_tx(bars + 8 * B_QF, O_BYTES);
        tma_2d(sb + OFF_QS, &m.qm, 80 * hg, 128 * r, bars + 8 * B_QF);
        tma_2d(sb + OFF_QT, &m.qt, 80 * hg + 64, 128 * r, bars + 8 * B_QF);
      }
    } else if (w == 1) {
      unsigned epoch = 0;
      if (lane == 0) {
        epoch = atomicAdd(g_cnt + C_LAUNCH, 1u) / NCTA;
        asm volatile("st.shared.u32 [%0], %1;" ::"r"(sb + OFF_EPOCH), "r"(epoch) : "memory");
        mbar_arrive(bars + 8 * B_EPOCH);
        mbar_wait(bars + 8 * B_KVD, 0);
        mbar_expect_tx(bars + 8 * B_HB, 5 * 4096);
#pragma unroll 1
        for (int c = 0; c < 5; c++) {
          if (c == 3) mbar_wait(bars + 8 * B_S3, 0);
          bulk_load(sb + off_ch(c) + U_BYTES, p.ssm_k + (5 * b + c) * SEQ, 4096, bars + 8 * B_HB);
        }
#pragma unroll
        for (int c = 0; c < 4; c++) mbar_expect_tx(bars + 8 * (B_U + c), c < 3 ? U_BYTES : 2 * U_BYTES);
        const uint4* usrc = g_U + 5 * b * U_PITCH;
        mbar_wait(bars + 8 * B_USIG, 0);
        flag_wait(g_cnt + C_PREP + 32 * (b & 15), (epoch + 1) * NCTA);
        TS(23);
#pragma unroll
        for (int c = 0; c < 5; c++) {
          if (c == 3) mbar_wait(bars + 8 * (B_U + 2), 0);
          if (c == 1) mbar_wait(bars + 8 * B_WOP, 0);
          bulk_load(sb + off_ch(c), usrc + c * U_PITCH, U_BYTES, bars + 8 * (B_U + (c < 3 ? c : 3)));
          TSIF(c == 0 || c == 4, 116 + (c >> 2));
        }
      }
      epoch = __shfl_sync(0xffffffffu, epoch, 0);
      if (lane < 8) {
        const int src = (b & ~7) | step_src(hg, lane);
        mbar_wait(bars + 8 * B_OSIG, 0);
        flag_wait(g_cnt + C_O + 32 * src, epoch + 1);
        if (lane >= 1 && lane < 4) bulk_load(sb + off_o(lane), g_O + src * 1280, O_BYTES, bars + 8 * (B_FULL2 + lane));
        __syncwarp(0xff);
        TS(21);
        if (lane == 5) bulk_load(sb + OFF_GATE, g_gate + 128 * r, 512, bars + 8 * (B_FULL2 + 5));
#pragma unroll 1
        for (int j = 4; j < 8; j++) {
          if (lane == j) {
            mbar_wait(bars + 8 * (j < 6 ? B_C34 : B_EMPTY2 + j - 6), 0);
            if (RF_GATE && j == 6) mbar_wait(bars + 8 * B_YSIG, 0);
            bulk_load(sb + off_o(j), g_O + src * 1280, O_BYTES, bars + 8 * (B_FULL2 + j));
          }
          __syncwarp(0xff);
        }
        TS(22);
      }
    } else if (w == 2) {
      mbar_wait(bars + 8 * B_PREP, 0);
      flag_signal(g_cnt + C_PREP, 16, lane);
      TS(25);
      if (lane == 0) mbar_arrive(bars + 8 * B_USIG);
      mbar_wait(bars + 8 * B_GATE, 0);
      if ((NOMB & 1) && lane == 0) asm volatile("fence.release.gpu;" ::: "memory");
      mbar_wait(bars + 8 * B_ATTN, 0);
      if (lane == 0) {
        if (O_DEFER) mbar_wait(bars + 8 * (B_U + 3), 0);
        asm volatile("cp.async.bulk.global.shared::cta.bulk_group [%0], [%1], 20480;\ncp.async.bulk.commit_group;\n"
                     "cp.async.bulk.wait_group 0;\nfence.proxy.async.global;" ::"l"(g_O + b * 1280), "r"(sb + OFF_OA) : "memory");
      }
      TS(74);
      if (!(NOMB & 1)) flag_signal(g_cnt + C_O + 32 * b, 1, lane);
      else {
        __syncwarp();
        unsigned v = 0;
#pragma unroll
        for (int i = 0; i < 5; i++) v ^= read_back(reinterpret_cast<const char*>(g_O + b * 1280) + (32 * i + lane) * 128 + 124);
        v = __reduce_or_sync(0xffffffffu, v & p.zero);
        if (lane == 0) flag_bump(g_cnt + C_O + 32 * b + v);
      }
      TS(26);
      if (lane == 0) mbar_arrive(bars + 8 * B_OSIG);
      if (!(NOMB & 4)) {
        mbar_wait(bars + 8 * B_WOP, 0);
        flag_signal(g_cnt + C_W + 32 * hg, 1, lane);
      }
      TS(73);
    } else {
      uint4* dst = g_WO + (hg * 8 + (r >> 1)) * 800 + (r & 1) * 80;
      if (lane == 0) {
        if (!WO_EARLY) {
          mbar_wait(bars + 8 * B_KVD, 0);
          mbar_wait(bars + 8 * WB_TRIG, 0);
          mbar_expect_tx(bars + 8 * B_WST, WO_BYTES / 2);
          tma_3d(sb + OFF_WS, &m.wo, 0, 40 * r, 5 * hg, bars + 8 * B_WST);
        }
        mbar_wait(bars + 8 * B_WST, 0);
        mbar_wait(bars + 8 * WO_TRIG, 0);
#pragma unroll 1
        for (int n = 0; n < 5; n++)
          asm volatile("cp.async.bulk.global.shared::cta.bulk_group [%0], [%1], 1280;" ::"l"(dst + 160 * n), "r"(sb + OFF_WS + 1280 * n) : "memory");
        asm volatile("cp.async.bulk.commit_group;\ncp.async.bulk.wait_group 0;\nfence.proxy.async.global;" ::: "memory");
        mbar_arrive(bars + 8 * B_WOP);
      }
      __syncwarp();
      unsigned v = 0;
      if (NOMB & 4) {
        if (lane < 25) v = read_back(dst + 160 * (lane / 5) + 16 * (lane % 5) + 7) ^ read_back(dst + 160 * (lane / 5) + 16 * (lane % 5) + 15);
        v = __reduce_or_sync(0xffffffffu, v & p.zero);
        if (lane == 0) flag_bump(g_cnt + C_W + 32 * hg + v);
      }
      TS(71);
#pragma unroll 1
      for (int c = 0; c < 5; c++) {
        if (lane == 0) {
          mbar_wait(bars + 8 * (B_YST + c), 0);
          asm volatile("cp.async.bulk.global.shared::cta.bulk_group [%0], [%1], 4096;\ncp.async.bulk.commit_group;\n"
                       "cp.async.bulk.wait_group 0;" ::"l"(g_Y + (5 * b + c) * Y_PITCH), "r"(sb + off_ch(c)) : "memory");
          if (c == 2) mbar_arrive(bars + 8 * B_C34);
        }
        __syncwarp();
        if (NOMB & 2) v ^= read_back(g_Y + (5 * b + c) * Y_PITCH + 8 * lane + 7);
      }
      TS(75);
      v = __reduce_or_sync(0xffffffffu, v & p.zero);
      if (lane == 0) {
        asm volatile("fence.proxy.async.global;" ::: "memory");
        if (!(NOMB & 2)) asm volatile("fence.release.gpu;" ::: "memory");
        flag_bump(g_cnt + C_Y + 32 * (b >> 4) + v);
        TS(27);
        mbar_arrive(bars + 8 * B_YSIG);
        mbar_expect_tx(bars + 8 * B_YFULL, 20480);
        flag_wait(g_cnt + C_Y + 32 * hg, (lds32(sb + OFF_EPOCH) + 1) * 16);
        TS(24);
        tma_2d(sb + OFF_YT, &m.y, 128 * r, 80 * hg, bars + 8 * B_YFULL);
        tma_2d(sb + OFF_YT + 10240, &m.y, 128 * r + 64, 80 * hg, bars + 8 * B_YFULL);
      }
    }
  } else {
    asm volatile("setmaxnreg.inc.sync.aligned.u32 152;");
    if (wg < 2) {
      float acc[120];
#pragma unroll
      for (int i = 0; i < 120; i++) acc[i] = 0.f;
      const uint32_t da = desc_lo(sb + wg * 8192, 16), db = desc_lo(sb + ST_W, 8192), dc = desc_lo(sb + ST_WT, 2048);
      if (PW1) pin<120>(acc);
      if (PW1 == 2) mbar_wait(bars + 8 * B_FULL1, 0);
#pragma unroll 1
      for (int kb = 0; kb < 10; kb++) {
        mbar_wait(bars + 8 * (B_FULL1 + (kb & 3)), (kb >> 2) & 1);
        const uint32_t so = (kb & 3) * (STAGE_BYTES >> 4);
        wg_fence();
#pragma unroll
        for (int k = 0; k < 4; k++) {
          WgSST<192>::mma<HI_SW128, HI_SW128>(acc, da + so + 2 * k, db + so + 128 * k, 1);
          WgSST<48>::mma<HI_SW128, HI_SW32>(acc + 96, da + so + 2 * k, dc + so + 32 * k, 1);
        }
        wg_commit();
        wg_wait<1>();
        if (kb > 0 && lane == 0) mbar_arrive(bars + 8 * (kb == 4 ? B_E3 : B_EMPTY1 + ((kb - 1) & 3)));
      }
      wg_wait<0>();
      pin<120>(acc);
      if (lane == 0) mbar_arrive(bars + 8 * B_P1);
      TSM(w == 0, 3 + wg);
      attention(acc, sb, b, wg, w, lane);
    } else {
      const int tw = tid & 127, chl = 64 * (b & 1) + 8 * w + (lane >> 2);
      uint4* up = g_U + chl * U_PITCH + ((4 * (b >> 1) + (lane & 3)) ^ ((b >> 2) & 1));
      uint2 sw[10];
      uint32_t dv = 0;
      if (lane < 5) dv = __ldg(reinterpret_cast<const unsigned short*>(p.ssm_D) + 5 * b + lane);
#pragma unroll
      for (int i = 0; i < 10; i++) sw[i] = ldg64(reinterpret_cast<const uint2*>(p.shift_k) + chl + 128 * (i >> 1) + 32 * (i & 1));
      uint32_t tab[12];
      fft_tables(tab, tw);
      uint4 res[10];
#pragma unroll
      for (int i = 0; i < 10; i++) res[i] = make_uint4(0, 0, 0, 0);
#pragma unroll 1
      for (int slab = 0; slab < 5; slab++) {
#pragma unroll
        for (int i = 0; i < 8; i++) res[i] = res[i + 2];
        prep_slab(res + 8, sw, sb, slab, w, lane);
        TSIF(w == 0, 99 + 4 * slab);
#pragma unroll
        for (int i = 0; i < 8; i++) sw[i] = sw[i + 2];
      }
      TSIF(w == 0, 28);
      __syncwarp();
      if (lane == 0) mbar_arrive(bars + 8 * B_KVD + ((res[8].x ^ res[9].x) & p.zero));
      mbar_wait(bars + 8 * B_KVD, 0);
      fft_tables_store(tab, sb, tw);
      mbar_wait(bars + 8 * B_LAST, 0);
#pragma unroll
      for (int i = 0; i < 10; i++) up[(128 * (i >> 1) + 32 * (i & 1)) * U_PITCH] = res[i];
      __syncwarp();
      if (lane == 0) mbar_arrive(bars + 8 * B_PREP);
      TSIF(w == 0, 5);
      mbar_wait(bars + 8 * (G_AFTER ? B_USIG : B_LAST), 0);
      prep_gate(p, b, w, lane);
      __syncwarp();
      if (lane == 0) mbar_arrive(bars + 8 * B_GATE);
      TSIF(w == 0, 72);
      mbar_wait(bars + 8 * B_HB, 0);
      TSIF(w == 0, 123);
      const uint32_t ha = sb + U_BYTES + ((tw >> 3) * 16 + 8 + (tw & 7)) * 16;
      uint4 hv[5];
#pragma unroll
      for (int c = 0; c < 5; c++) hv[c] = lds128(ha + off_ch(c));
      __syncwarp();
#pragma unroll
      for (int c = 0; c < 5; c++) sts128((ha ^ 16) + off_ch(c), hv[c].x, hv[c].y, hv[c].z, hv[c].w);
      if (tw < 5) asm volatile("st.shared.f32 [%0], %1;" ::"r"(sb + OFF_D + 4 * tw), "f"(bf_lo(dv) * 0.125f) : "memory");
      fence_async_smem();
      __syncwarp();
      if (lane == 0) mbar_arrive(bars + 8 * B_HA);
      TSIF(w == 0, 6);
    }

    FftConst fc;
    fft_twiddles(fc, w, lane);
    mbar_wait(bars + 8 * B_HA, 0);
    fft_matrices(fc, sb, w, lane);
    if (ATT_GATE && !H_EARLY) mbar_wait(bars + 8 * B_ATTN, 0);
    TSIF(w == 0 && wg == 2, 124);
#pragma unroll 1
    for (int c = wg == 2 ? 0 : wg + 1; c < 5; c += 3) {
      conv_channel(fc, sb, c, wg, w, lane);
      if (lane == 0) mbar_arrive(bars + 8 * (B_YST + c));
      TSM(w == 0, 10 + c);
    }

    if (wg < 2) {
      const int g = lane >> 2;
      float acc[40];
#pragma unroll
      for (int i = 0; i < 40; i++) acc[i] = 0.f;
      const uint32_t da = desc_lo(sb + wg * 1024, 2048), db = desc_lo(sb, 2560);
      mbar_wait(bars + 8 * B_ATTN, 0);
      mbar_wait(bars + 8 * (B_YST + 3), 0);
      mbar_wait(bars + 8 * (B_YST + 4), 0);
      if (PW2) mbar_wait(bars + 8 * B_FULL2, 0);
#pragma unroll 1
      for (int j = 0; j < 8; j++) {
        mbar_wait(bars + 8 * (B_FULL2 + j), 0);
        const uint32_t oa = da + (off_o(j) >> 4), ob = db + (off_w(j) >> 4);
        wg_fence();
#pragma unroll
        for (int k = 0; k < 5; k++) WgSST<80>::mma<HI_NONE, HI_SW32>(acc, oa + 256 * k, ob + 32 * k, 1);
        wg_commit();
        wg_wait<1>();
        if (j >= 1 && j <= 4 && lane == 0) mbar_arrive(bars + 8 * (B_EMPTY2 + j - 1));
      }
      TSIF(w == 0 && wg == 0, 113);
      const int tr = 64 * wg + 16 * w + (lane & 15);
      const uint32_t fm = sb + OFF_QS + tr * 128, fx = (lane >> 4) ^ (tr & 7);
      const uint32_t ft = sb + OFF_QT + tr * 32 + (((lane >> 4) ^ (tr >> 2)) & 1) * 16;
      const float g0 = __uint_as_float(lds32(sb + OFF_GATE + (64 * wg + 16 * w + g) * 4));
      const float g1 = __uint_as_float(lds32(sb + OFF_GATE + (64 * wg + 16 * w + 8 + g) * 4));
      const uint32_t ga = pack2(g0, g0), gb = pack2(g1, g1);
      const uint32_t na = pack2(1.f - g0, 1.f - g0), nb = pack2(1.f - g1, 1.f - g1);

      wg_wait<0>();
      pin<40>(acc);
      TSM(w == 0, 17 + wg);
      uint32_t pb[20];
#pragma unroll
      for (int j = 0; j < 10; j++) {
        pb[2 * j] = bmul(na, pack2(acc[4 * j], acc[4 * j + 1]));
        pb[2 * j + 1] = bmul(nb, pack2(acc[4 * j + 2], acc[4 * j + 3]));
        asm volatile("" : "+r"(pb[2 * j]), "+r"(pb[2 * j + 1]));
      }
      const uint32_t ya = sb + OFF_YT + wg * 10240 + ((lane >> 4) * 8 + (lane & 7)) * 128 +
                          (((2 * w + (((lane >> 3) & 1) ^ wg)) ^ (lane & 7)) << 4);
      uint32_t qf[20];
      mbar_wait(bars + 8 * B_QF, 0);
#pragma unroll
      for (int j = 0; j < 5; j++) ldsm4(qf + 4 * j, j < 4 ? fm + ((fx ^ (2 * j)) << 4) : ft);
      mbar_wait(bars + 8 * B_YFULL, 0);
      TSIF(w == 0 && wg == 0, 19);
#pragma unroll
      for (int j = 0; j < 5; j++) {
        uint32_t y[4];
        ldsm4t(y, ya + 2048 * j);
#pragma unroll
        for (int i = 0; i < 4; i++) qf[4 * j + i] = badd(bmul((i & 1) ? gb : ga, bmul(qf[4 * j + i], y[i])), pb[4 * j + i]);
      }
#pragma unroll
      for (int j = 0; j < 5; j++) stsm4(j < 4 ? fm + ((fx ^ (2 * j)) << 4) : ft, qf + 4 * j);
      fence_async_smem();
      __syncwarp();
      if (lane == 0) {
        const int row = 64 * wg + 16 * w;
        asm volatile("cp.async.bulk.tensor.2d.global.shared::cta.bulk_group [%0, {%2, %3}], [%1];"
                     ::"l"(&m.om), "r"(sb + OFF_QS + row * 128), "r"(80 * hg), "r"(128 * r + row) : "memory");
        asm volatile("cp.async.bulk.tensor.2d.global.shared::cta.bulk_group [%0, {%2, %3}], [%1];"
                     ::"l"(&m.ot), "r"(sb + OFF_QT + row * 32), "r"(80 * hg + 64), "r"(128 * r + row) : "memory");
        asm volatile("cp.async.bulk.commit_group;\ncp.async.bulk.wait_group.read 0;" ::: "memory");
      }
      TSM(true, 40 + 4 * wg + w);
      if (ENDBAR) asm volatile("bar.sync 15, 256;" ::: "memory");
    }
  }
}

typedef CUresult (*EncodeFn)(CUtensorMap*, CUtensorMapDataType, cuuint32_t, void*, const cuuint64_t*, const cuuint64_t*,
                             const cuuint32_t*, const cuuint32_t*, CUtensorMapInterleave, CUtensorMapSwizzle,
                             CUtensorMapL2promotion, CUtensorMapFloatOOBfill);

void encode(EncodeFn fn, CUtensorMap* tm, const void* base, int rank, const cuuint64_t* dims, const cuuint64_t* strides,
            const cuuint32_t* box, CUtensorMapSwizzle swz) {
  const cuuint32_t ones[3] = {1, 1, 1};
  fn(tm, CU_TENSOR_MAP_DATA_TYPE_BFLOAT16, rank, const_cast<void*>(base), dims, strides, box, ones,
     CU_TENSOR_MAP_INTERLEAVE_NONE, swz, CU_TENSOR_MAP_L2_PROMOTION_L2_128B, CU_TENSOR_MAP_FLOAT_OOB_FILL_NONE);
}

}

extern "C" void kernel_launch(void* const* d_in, const int* in_sizes, int n_in, void* d_out, int out_size) {
  (void)in_sizes; (void)n_in; (void)out_size;
  Params p;
  p.q = (const __nv_bfloat16*)d_in[0];
  p.k = (const __nv_bfloat16*)d_in[1];
  p.v = (const __nv_bfloat16*)d_in[2];
  p.shift_k = (const __nv_bfloat16*)d_in[3];
  p.ssm_k = (const __nv_bfloat16*)d_in[4];
  p.ssm_D = (const __nv_bfloat16*)d_in[5];
  p.wqkv = (const __nv_bfloat16*)d_in[7];
  p.wo = (const __nv_bfloat16*)d_in[8];
  p.gate_w = (const __nv_bfloat16*)d_in[9];
  p.out = (__nv_bfloat16*)d_out;
  p.zero = 0;

  static EncodeFn fn = nullptr;
  static void* yaddr = nullptr;
  if (!fn) {
    cudaDriverEntryPointQueryResult qr;
    void* f = nullptr;
    cudaGetDriverEntryPoint("cuTensorMapEncodeTiled", &f, cudaEnableDefault, &qr);
    fn = (EncodeFn)f;
    cudaGetSymbolAddress(&yaddr, g_Y);
    cudaFuncSetAttribute(fused_kernel, cudaFuncAttributeMaxDynamicSharedMemorySize, SMEM_BYTES);
  }
  Maps m;
  {
    const cuuint64_t dims[3] = {640, 1024, 2}, st[2] = {2560, 1280};
    const cuuint32_t box[3] = {64, 64, 2};
    encode(fn, &m.x, p.q, 3, dims, st, box, CU_TENSOR_MAP_SWIZZLE_128B);
  }
  {
    const cuuint64_t dims[3] = {640, 640, 3}, st[2] = {3840, 1280};
    const cuuint32_t box[3] = {64, 64, 3}, boxt[3] = {16, 64, 3};
    encode(fn, &m.wm, p.wqkv, 3, dims, st, box, CU_TENSOR_MAP_SWIZZLE_128B);
    encode(fn, &m.wt, p.wqkv, 3, dims, st, boxt, CU_TENSOR_MAP_SWIZZLE_32B);
  }
  {
    const cuuint64_t dims[3] = {64, 2048, 10}, st[2] = {1280, 128};
    const cuuint32_t boxk[3] = {64, 35, 1}, boxv[3] = {64, 32, 1};
    encode(fn, &m.k, p.k, 3, dims, st, boxk, CU_TENSOR_MAP_SWIZZLE_128B);
    encode(fn, &m.v, p.v, 3, dims, st, boxv, CU_TENSOR_MAP_SWIZZLE_128B);
  }
  {
    const cuuint64_t dims[3] = {16, 640, 40}, st[2] = {1280, 32};
    const cuuint32_t box[3] = {16, 40, 5};
    encode(fn, &m.wo, p.wo, 3, dims, st, box, CU_TENSOR_MAP_SWIZZLE_32B);
  }
  {
    const cuuint64_t dims[2] = {2048, 640}, st[1] = {Y_PITCH * 16};
    const cuuint32_t box[2] = {64, 80};
    encode(fn, &m.y, yaddr, 2, dims, st, box, CU_TENSOR_MAP_SWIZZLE_128B);
  }
  {
    const cuuint64_t dims[2] = {640, 2048}, st[1] = {1280};
    const cuuint32_t bqm[2] = {64, 128}, bqt[2] = {16, 128}, bom[2] = {64, 16}, bot[2] = {16, 16};
    encode(fn, &m.qm, p.q, 2, dims, st, bqm, CU_TENSOR_MAP_SWIZZLE_128B);
    encode(fn, &m.qt, p.q, 2, dims, st, bqt, CU_TENSOR_MAP_SWIZZLE_32B);
    encode(fn, &m.om, p.out, 2, dims, st, bom, CU_TENSOR_MAP_SWIZZLE_128B);
    encode(fn, &m.ot, p.out, 2, dims, st, bot, CU_TENSOR_MAP_SWIZZLE_32B);
  }
  fused_kernel<<<NCTA, NTHR, SMEM_BYTES>>>(m, p);
}
```

```cpp
#include <cuda.h>
#include <cuda_bf16.h>
#include <cuda_runtime.h>
#include <stdint.h>

namespace {

constexpr int SEQ = 2048, DIM = 640, NCTA = 128, NTHR = 512;

#define TRIG_KB 9
#define KV_KB 2
#define DEV_EXIT 0
#define ATT_GATE 1
#define G_AFTER 0
#define FENCE_LO 0
#define FENCE_HI 0
#define PW1 2
#define PW2 1
#define ENDBAR 0
#define PAD_KB 0
#define Y_ALIAS 1
#define H_EARLY 1
#define NOMB 0
#define SRC_ROT 0
#define WAIT_NS 0
#define WB_TRIG B_USIG
#define G_POS 0
#define TAILF 1
#define T_ISSUE 384
#define T_PF 416
#define T_INIT 448
#define ATT_MERGE 0
#define BMAP 1
#define PRE2 1
#define KV_MIX 0
#define O_DEFER 0
#define TOK_G 1
#define RF_GATE 0
#define WO_TRIG B_WST
#define WL_TRIG B_WOP
#define WO_GATE 1

constexpr uint32_t STAGE_BYTES = 47104, ST_W = 16384, ST_WT = 40960;
constexpr uint32_t O_BYTES = 20480, WO_BYTES = 12800;
constexpr uint32_t OFF_OA = 0;
constexpr uint32_t OFF_QS = 3 * O_BYTES, OFF_QT = OFF_QS + 16384;
constexpr uint32_t OFF_WC = 81920;
constexpr uint32_t OFF_WA = 94720;
constexpr uint32_t OFF_GATE = 145920;
constexpr uint32_t OFF_KVX = 147968;
constexpr uint32_t OFF_D = OFF_GATE + 512;
constexpr uint32_t OFF_CH3 = 163840;
constexpr uint32_t CH_BYTES = 12288, U_BYTES = 4096;
constexpr uint32_t OFF_FT = 225280, OFF_GT = 229376;
constexpr uint32_t OFF_CH0 = 188416;
constexpr uint32_t OFF_KVS = OFF_CH0, KVS_V = 4480, KVS_BYTES = 8576;
constexpr uint32_t OFF_WS = OFF_WA;
constexpr uint32_t OFF_YT = 163840;
constexpr uint32_t OFF_BAR = 231936;
constexpr uint32_t SMEM_BYTES = OFF_BAR + 512;

enum : uint32_t {
  B_FULL1 = 0, B_EMPTY1 = 4, B_S3 = 7, B_FULL2 = 52, B_EMPTY2 = 13, B_U = 8, B_GATE = 12, B_HA = 19, B_HB = 20,
  B_ATTN = 21, B_C34 = 22, B_CONV = 23, B_YFULL = 24, B_EPOCH = 25, B_PREP = 26, B_P1 = 27, B_LAST = 28,
  B_E3 = 29, B_OSIG = 30, B_WOP = 31, B_USIG = 32, B_WST = 33, B_KV = 34, B_KVD = 39, B_HC = 61, B_QF = 62, B_YST = 40,
  B_TOK = 45, B_YSIG = 50
};
constexpr uint32_t OFF_EPOCH = OFF_BAR + 8 * 51;
__device__ __forceinline__ uint32_t off_o(int j) { return j < 4 ? OFF_OA + j * O_BYTES : j < 6 ? OFF_CH0 + (j - 4) * O_BYTES : OFF_OA + (j - 6) * O_BYTES; }
__device__ __forceinline__ uint32_t off_w(int j) { return j < 4 ? OFF_WA + j * WO_BYTES : j == 4 ? OFF_KVX : j == 5 ? OFF_WC : OFF_WA + (j - 6) * WO_BYTES; }
__device__ __forceinline__ int step_src(int hg, int j) { return SRC_ROT ? (hg + j) & 7 : j == 0 ? hg : j <= hg ? j - 1 : j; }
__device__ __forceinline__ bool tail_first(int hg) { return TAILF && (hg & 3) == 3; }
__device__ __forceinline__ uint32_t off_ch(int c) { return (c < 3 ? OFF_CH0 : OFF_CH3 - 3 * CH_BYTES) + c * CH_BYTES; }

#define U_PITCH 264
__device__ __align__(1024) uint4 g_U[DIM * U_PITCH];
__device__ uint4 g_O[NCTA * 1280];
#define g_Y g_U
constexpr int Y_PITCH = U_PITCH;
__device__ uint4 g_WO[64 * 800];
__device__ uint4 g_halo[NCTA * 2 * 7 * 32];
__device__ float g_gate[SEQ + PAD_KB * 256];
__device__ unsigned g_cnt[32 * (1 + 2 * 16 + 8 + NCTA)];
constexpr int C_LAUNCH = 0, C_PREP = 32, C_Y = 32 * 17, C_W = 32 * 33, C_O = 32 * 41;

#define TSM(cond, slot) do { } while (0)
#define TSIF(cond, slot) do { if (__LINE__ >= FENCE_LO && __LINE__ < FENCE_HI) sched_fence(); } while (0)
__device__ __forceinline__ void sched_fence() {
  asm volatile("{\n.reg .pred p;\n.reg .u32 c;\nmov.u32 c, %%clock;\nsetp.eq.u32 p, c, 0;\n@p st.shared.u32 [%0], c;\n}"
               ::"r"(1024 + OFF_EPOCH + 4) : "memory");
}
#define TS(slot) TSIF(true, slot)

struct Params {
  const __nv_bfloat16 *q, *k, *v, *shift_k, *ssm_k, *ssm_D, *wqkv, *wo, *gate_w;
  __nv_bfloat16* out;
  uint32_t zero;
};

#define POLL_NS 0
constexpr int SPIN_LIMIT = 1 << 17;

__device__ __forceinline__ void mbar_init(uint32_t bar, uint32_t count) {
  asm volatile("mbarrier.init.shared::cta.b64 [%0], %1;" ::"r"(bar), "r"(count) : "memory");
}
__device__ __forceinline__ void mbar_expect_tx(uint32_t bar, uint32_t bytes) {
  asm volatile("mbarrier.arrive.expect_tx.shared::cta.b64 _, [%0], %1;" ::"r"(bar), "r"(bytes) : "memory");
}
__device__ __forceinline__ void mbar_arrive(uint32_t bar) {
  asm volatile("mbarrier.arrive.shared::cta.b64 _, [%0];" ::"r"(bar) : "memory");
}
__device__ __forceinline__ void mbar_wait(uint32_t bar, uint32_t parity) {
  uint32_t ok;
  int spins = 0;
  do {
    if (WAIT_NS)
      asm volatile("{\n.reg .pred p;\nmbarrier.try_wait.parity.shared::cta.b64 p, [%1], %2, %3;\nselp.b32 %0, 1, 0, p;\n}"
                   : "=r"(ok) : "r"(bar), "r"(parity), "r"(WAIT_NS) : "memory");
    else
      asm volatile("{\n.reg .pred p;\nmbarrier.try_wait.parity.shared::cta.b64 p, [%1], %2;\nselp.b32 %0, 1, 0, p;\n}"
                   : "=r"(ok) : "r"(bar), "r"(parity) : "memory");
    if (++spins > SPIN_LIMIT) break;
  } while (!ok);
}
__device__ __forceinline__ void flag_poll(const unsigned* p, unsigned target) {
  unsigned v;
  int spins = 0;
  do {
    if (POLL_NS && spins) __nanosleep(POLL_NS);
    asm volatile("ld.relaxed.gpu.global.u32 %0, [%1];" : "=r"(v) : "l"(p) : "memory");
    if (++spins > SPIN_LIMIT) break;
  } while ((int)(v - target) < 0);
}
__device__ __forceinline__ void flag_wait(const unsigned* p, unsigned target) {
  flag_poll(p, target);
  asm volatile("fence.acquire.gpu;\nfence.proxy.async.global;" ::: "memory");
}
__device__ __forceinline__ void flag_signal(unsigned* p, int n, int lane) {
  if (lane == 0) asm volatile("fence.release.gpu;" ::: "memory");
  __syncwarp();
  if (lane < n) asm volatile("red.relaxed.gpu.global.add.u32 [%0], 1;" ::"l"(p + 32 * lane) : "memory");
}
__device__ __forceinline__ void flag_bump(unsigned* p) {
  asm volatile("red.relaxed.gpu.global.add.u32 [%0], 1;" ::"l"(p) : "memory");
}
__device__ __forceinline__ void fence_async_smem() { asm volatile("fence.proxy.async.shared::cta;" ::: "memory"); }
__device__ __forceinline__ void wg_sync(int id) { asm volatile("bar.sync %0, 128;" ::"r"(id) : "memory"); }

__device__ __forceinline__ void tma_2d(uint32_t dst, const CUtensorMap* tm, int c0, int c1, uint32_t bar) {
  asm volatile("cp.async.bulk.tensor.2d.shared::cluster.global.mbarrier::complete_tx::bytes [%0], [%1, {%3, %4}], [%2];"
               ::"r"(dst), "l"(tm), "r"(bar), "r"(c0), "r"(c1) : "memory");
}
__device__ __forceinline__ void tma_3d(uint32_t dst, const CUtensorMap* tm, int c0, int c1, int c2, uint32_t bar) {
  asm volatile("cp.async.bulk.tensor.3d.shared::cluster.global.mbarrier::complete_tx::bytes [%0], [%1, {%3, %4, %5}], [%2];"
               ::"r"(dst), "l"(tm), "r"(bar), "r"(c0), "r"(c1), "r"(c2) : "memory");
}
__device__ __forceinline__ void bulk_load(uint32_t dst, const void* src, uint32_t bytes, uint32_t bar) {
  asm volatile("cp.async.bulk.shared::cluster.global.mbarrier::complete_tx::bytes [%0], [%1], %2, [%3];"
               ::"r"(dst), "l"(src), "r"(bytes), "r"(bar) : "memory");
}
__device__ __forceinline__ void tm_prefetch(const CUtensorMap* tm) {
  asm volatile("prefetch.tensormap [%0];" ::"l"(tm) : "memory");
}

__device__ __forceinline__ void wg_fence() { asm volatile("wgmma.fence.sync.aligned;" ::: "memory"); }
__device__ __forceinline__ void wg_commit() { asm volatile("wgmma.commit_group.sync.aligned;" ::: "memory"); }
template <int N> __device__ __forceinline__ void wg_wait() { asm volatile("wgmma.wait_group.sync.aligned %0;" ::"n"(N) : "memory"); }
__device__ __forceinline__ uint32_t desc_lo(uint32_t addr, uint32_t lbo) { return ((addr & 0x3FFFF) >> 4) | ((lbo >> 4) << 16); }
constexpr uint32_t desc_hi(uint32_t sbo, uint32_t swz) { return (sbo >> 4) | (swz << 30); }
constexpr uint32_t HI_SW128 = desc_hi(1024, 1), HI_SW64 = desc_hi(512, 2), HI_SW32 = desc_hi(256, 3), HI_NONE = desc_hi(128, 0);
template <int N> __device__ __forceinline__ void pin(float* d) {
#pragma unroll
  for (int i = 0; i < N; i++) asm volatile("" : "+f"(d[i])::"memory");
}

__device__ __forceinline__ uint32_t lds32(uint32_t a) {
  uint32_t v;
  asm volatile("ld.volatile.shared.u32 %0, [%1];" : "=r"(v) : "r"(a) : "memory");
  return v;
}
__device__ __forceinline__ uint4 ldg128(const void* a) {
  uint4 v;
  asm volatile("ld.global.nc.v4.u32 {%0, %1, %2, %3}, [%4];" : "=r"(v.x), "=r"(v.y), "=r"(v.z), "=r"(v.w) : "l"(a) : "memory");
  return v;
}
__device__ __forceinline__ uint2 ldg64(const void* a) {
  uint2 v;
  asm volatile("ld.global.nc.v2.u32 {%0, %1}, [%2];" : "=r"(v.x), "=r"(v.y) : "l"(a) : "memory");
  return v;
}
__device__ __forceinline__ void ldsm4(uint32_t* r, uint32_t a) {
  asm volatile("ldmatrix.sync.aligned.m8n8.x4.shared.b16 {%0, %1, %2, %3}, [%4];"
               : "=r"(r[0]), "=r"(r[1]), "=r"(r[2]), "=r"(r[3]) : "r"(a) : "memory");
}
__device__ __forceinline__ void ldsm4t(uint32_t* r, uint32_t a) {
  asm volatile("ldmatrix.sync.aligned.m8n8.x4.trans.shared.b16 {%0, %1, %2, %3}, [%4];"
               : "=r"(r[0]), "=r"(r[1]), "=r"(r[2]), "=r"(r[3]) : "r"(a) : "memory");
}
__device__ __forceinline__ uint4 lds128(uint32_t a) {
  uint4 v;
  asm volatile("ld.shared.v4.u32 {%0, %1, %2, %3}, [%4];" : "=r"(v.x), "=r"(v.y), "=r"(v.z), "=r"(v.w) : "r"(a) : "memory");
  return v;
}
__device__ __forceinline__ void sts128(uint32_t a, uint32_t x, uint32_t y, uint32_t z, uint32_t w) {
  asm volatile("st.shared.v4.u32 [%0], {%1, %2, %3, %4};" ::"r"(a), "r"(x), "r"(y), "r"(z), "r"(w) : "memory");
}
__device__ __forceinline__ void stsm4(uint32_t a, const uint32_t* r) {
  asm volatile("stmatrix.sync.aligned.m8n8.x4.shared.b16 [%0], {%1, %2, %3, %4};" ::"r"(a), "r"(r[0]), "r"(r[1]), "r"(r[2]), "r"(r[3]) : "memory");
}
__device__ __forceinline__ void stsm4t(uint32_t a, const uint32_t* r) {
  asm volatile("stmatrix.sync.aligned.m8n8.x4.trans.shared.b16 [%0], {%1, %2, %3, %4};" ::"r"(a), "r"(r[0]), "r"(r[1]), "r"(r[2]), "r"(r[3]) : "memory");
}
__device__ __forceinline__ uint32_t pack2(float lo, float hi) {
  uint32_t r;
  asm("cvt.rn.bf16x2.f32 %0, %1, %2;" : "=r"(r) : "f"(hi), "f"(lo));
  return r;
}
__device__ __forceinline__ uint32_t movm(uint32_t a) {
  uint32_t d;
  asm volatile("movmatrix.sync.aligned.m8n8.trans.b16 %0, %1;" : "=r"(d) : "r"(a));
  return d;
}
__device__ __forceinline__ uint32_t bmul(uint32_t a, uint32_t b) {
  uint32_t d;
  asm("mul.rn.bf16x2 %0, %1, %2;" : "=r"(d) : "r"(a), "r"(b));
  return d;
}
__device__ __forceinline__ uint32_t badd(uint32_t a, uint32_t b) {
  uint32_t d;
  asm("add.rn.bf16x2 %0, %1, %2;" : "=r"(d) : "r"(a), "r"(b));
  return d;
}
__device__ __forceinline__ float bf_lo(uint32_t x) { return __uint_as_float(x << 16); }
__device__ __forceinline__ float bf_hi(uint32_t x) { return __uint_as_float(x & 0xFFFF0000u); }
__device__ __forceinline__ float ex2(float x) {
  float y;
  asm("ex2.approx.ftz.f32 %0, %1;" : "=f"(y) : "f"(x));
  return y;
}
__device__ __forceinline__ float rcp(float x) {
  float y;
  asm("rcp.approx.ftz.f32 %0, %1;" : "=f"(y) : "f"(x));
  return y;
}
__device__ __forceinline__ void mma16816(float* d, uint32_t a0, uint32_t a1, uint32_t a2, uint32_t a3, uint32_t b0, uint32_t b1) {
  asm volatile("mma.sync.aligned.m16n8k16.row.col.f32.bf16.bf16.f32 {%0, %1, %2, %3}, {%4, %5, %6, %7}, {%8, %9}, {%0, %1, %2, %3};"
               : "+f"(d[0]), "+f"(d[1]), "+f"(d[2]), "+f"(d[3])
               : "r"(a0), "r"(a1), "r"(a2), "r"(a3), "r"(b0), "r"(b1));
}
__device__ __forceinline__ void mma1688(float* d, uint32_t a0, uint32_t a1, uint32_t b0) {
  asm volatile("mma.sync.aligned.m16n8k8.row.col.f32.bf16.bf16.f32 {%0, %1, %2, %3}, {%4, %5}, {%6}, {%0, %1, %2, %3};"
               : "+f"(d[0]), "+f"(d[1]), "+f"(d[2]), "+f"(d[3])
               : "r"(a0), "r"(a1), "r"(b0));
}

template <int N> struct WgRS;
template <int N> struct WgSST;
template <> struct WgRS<32> {
  template <uint32_t HB>
  static __device__ __forceinline__ void mma(float* d, const uint32_t* a, uint32_t db) {
    asm volatile("{\n.reg .pred p;\n.reg .b64 db;\nsetp.ne.b32 p, %22, 0;\n"
      "mov.b64 db, {%20, %21};\n"
      "wgmma.mma_async.sync.aligned.m64n32k16.f32.bf16.bf16 {"
      "%0, %1, %2, %3, %4, %5, %6, %7, %8, %9, %10, %11, %12, %13, %14, %15"
      "}, {%16, %17, %18, %19}, db, p, 1, 1, 1;\n}\n"
      : "+f"(d[0]), "+f"(d[1]), "+f"(d[2]), "+f"(d[3]), "+f"(d[4]), "+f"(d[5]), "+f"(d[6]), "+f"(d[7]),
        "+f"(d[8]), "+f"(d[9]), "+f"(d[10]), "+f"(d[11]), "+f"(d[12]), "+f"(d[13]), "+f"(d[14]), "+f"(d[15])
      : "r"(a[0]), "r"(a[1]), "r"(a[2]), "r"(a[3]), "r"(db), "n"(HB), "n"(1));
  }
  template <uint32_t HB>
  static __device__ __forceinline__ void set(float* d, const uint32_t* a, uint32_t db) {
    asm volatile("{\n.reg .pred p;\n.reg .b64 db;\nsetp.ne.b32 p, %22, 0;\n"
      "mov.b64 db, {%20, %21};\n"
      "wgmma.mma_async.sync.aligned.m64n32k16.f32.bf16.bf16 {"
      "%0, %1, %2, %3, %4, %5, %6, %7, %8, %9, %10, %11, %12, %13, %14, %15"
      "}, {%16, %17, %18, %19}, db, p, 1, 1, 1;\n}\n"
      : "=f"(d[0]), "=f"(d[1]), "=f"(d[2]), "=f"(d[3]), "=f"(d[4]), "=f"(d[5]), "=f"(d[6]), "=f"(d[7]),
        "=f"(d[8]), "=f"(d[9]), "=f"(d[10]), "=f"(d[11]), "=f"(d[12]), "=f"(d[13]), "=f"(d[14]), "=f"(d[15])
      : "r"(a[0]), "r"(a[1]), "r"(a[2]), "r"(a[3]), "r"(db), "n"(HB), "n"(0));
  }
};
template <> struct WgRS<64> {
  template <uint32_t HB>
  static __device__ __forceinline__ void mma(float* d, const uint32_t* a, uint32_t db) {
    asm volatile("{\n.reg .pred p;\n.reg .b64 db;\nsetp.ne.b32 p, %38, 0;\n"
      "mov.b64 db, {%36, %37};\n"
      "wgmma.mma_async.sync.aligned.m64n64k16.f32.bf16.bf16 {"
      "%0, %1, %2, %3, %4, %5, %6, %7, %8, %9, %10, %11, %12, %13, %14, %15, "
      "%16, %17, %18, %19, %20, %21, %22, %23, %24, %25, %26, %27, %28, %29, %30, %31"
      "}, {%32, %33, %34, %35}, db, p, 1, 1, 1;\n}\n"
      : "+f"(d[0]), "+f"(d[1]), "+f"(d[2]), "+f"(d[3]), "+f"(d[4]), "+f"(d[5]), "+f"(d[6]), "+f"(d[7]),
        "+f"(d[8]), "+f"(d[9]), "+f"(d[10]), "+f"(d[11]), "+f"(d[12]), "+f"(d[13]), "+f"(d[14]), "+f"(d[15]),
        "+f"(d[16]), "+f"(d[17]), "+f"(d[18]), "+f"(d[19]), "+f"(d[20]), "+f"(d[21]), "+f"(d[22]), "+f"(d[23]),
        "+f"(d[24]), "+f"(d[25]), "+f"(d[26]), "+f"(d[27]), "+f"(d[28]), "+f"(d[29]), "+f"(d[30]), "+f"(d[31])
      : "r"(a[0]), "r"(a[1]), "r"(a[2]), "r"(a[3]), "r"(db), "n"(HB), "n"(1));
  }
  template <uint32_t HB>
  static __device__ __forceinline__ void set(float* d, const uint32_t* a, uint32_t db) {
    asm volatile("{\n.reg .pred p;\n.reg .b64 db;\nsetp.ne.b32 p, %38, 0;\n"
      "mov.b64 db, {%36, %37};\n"
      "wgmma.mma_async.sync.aligned.m64n64k16.f32.bf16.bf16 {"
      "%0, %1, %2, %3, %4, %5, %6, %7, %8, %9, %10, %11, %12, %13, %14, %15, "
      "%16, %17, %18, %19, %20, %21, %22, %23, %24, %25, %26, %27, %28, %29, %30, %31"
      "}, {%32, %33, %34, %35}, db, p, 1, 1, 1;\n}\n"
      : "=f"(d[0]), "=f"(d[1]), "=f"(d[2]), "=f"(d[3]), "=f"(d[4]), "=f"(d[5]), "=f"(d[6]), "=f"(d[7]),
        "=f"(d[8]), "=f"(d[9]), "=f"(d[10]), "=f"(d[11]), "=f"(d[12]), "=f"(d[13]), "=f"(d[14]), "=f"(d[15]),
        "=f"(d[16]), "=f"(d[17]), "=f"(d[18]), "=f"(d[19]), "=f"(d[20]), "=f"(d[21]), "=f"(d[22]), "=f"(d[23]),
        "=f"(d[24]), "=f"(d[25]), "=f"(d[26]), "=f"(d[27]), "=f"(d[28]), "=f"(d[29]), "=f"(d[30]), "=f"(d[31])
      : "r"(a[0]), "r"(a[1]), "r"(a[2]), "r"(a[3]), "r"(db), "n"(HB), "n"(0));
  }
};
template <> struct WgSST<48> {
  template <uint32_t HA, uint32_t HB>
  static __device__ __forceinline__ void mma(float* d, uint32_t da, uint32_t db, int sc) {
    asm volatile("{\n.reg .pred p;\n.reg .b64 da, db;\nsetp.ne.b32 p, %28, 0;\n"
      "mov.b64 da, {%24, %25};\nmov.b64 db, {%26, %27};\n"
      "wgmma.mma_async.sync.aligned.m64n48k16.f32.bf16.bf16 {"
      "%0, %1, %2, %3, %4, %5, %6, %7, %8, %9, %10, %11, %12, %13, %14, %15, "
      "%16, %17, %18, %19, %20, %21, %22, %23"
      "}, da, db, p, 1, 1, 0, 1;\n}\n"
      : "+f"(d[0]), "+f"(d[1]), "+f"(d[2]), "+f"(d[3]), "+f"(d[4]), "+f"(d[5]), "+f"(d[6]), "+f"(d[7]),
        "+f"(d[8]), "+f"(d[9]), "+f"(d[10]), "+f"(d[11]), "+f"(d[12]), "+f"(d[13]), "+f"(d[14]), "+f"(d[15]),
        "+f"(d[16]), "+f"(d[17]), "+f"(d[18]), "+f"(d[19]), "+f"(d[20]), "+f"(d[21]), "+f"(d[22]), "+f"(d[23])
      : "r"(da), "n"(HA), "r"(db), "n"(HB), "r"(sc));
  }
};
template <> struct WgSST<80> {
  template <uint32_t HA, uint32_t HB>
  static __device__ __forceinline__ void mma(float* d, uint32_t da, uint32_t db, int sc) {
    asm volatile("{\n.reg .pred p;\n.reg .b64 da, db;\nsetp.ne.b32 p, %44, 0;\n"
      "mov.b64 da, {%40, %41};\nmov.b64 db, {%42, %43};\n"
      "wgmma.mma_async.sync.aligned.m64n80k16.f32.bf16.bf16 {"
      "%0, %1, %2, %3, %4, %5, %6, %7, %8, %9, %10, %11, %12, %13, %14, %15, "
      "%16, %17, %18, %19, %20, %21, %22, %23, %24, %25, %26, %27, %28, %29, %30, %31, "
      "%32, %33, %34, %35, %36, %37, %38, %39"
      "}, da, db, p, 1, 1, 0, 1;\n}\n"
      : "+f"(d[0]), "+f"(d[1]), "+f"(d[2]), "+f"(d[3]), "+f"(d[4]), "+f"(d[5]), "+f"(d[6]), "+f"(d[7]),
        "+f"(d[8]), "+f"(d[9]), "+f"(d[10]), "+f"(d[11]), "+f"(d[12]), "+f"(d[13]), "+f"(d[14]), "+f"(d[15]),
        "+f"(d[16]), "+f"(d[17]), "+f"(d[18]), "+f"(d[19]), "+f"(d[20]), "+f"(d[21]), "+f"(d[22]), "+f"(d[23]),
        "+f"(d[24]), "+f"(d[25]), "+f"(d[26]), "+f"(d[27]), "+f"(d[28]), "+f"(d[29]), "+f"(d[30]), "+f"(d[31]),
        "+f"(d[32]), "+f"(d[33]), "+f"(d[34]), "+f"(d[35]), "+f"(d[36]), "+f"(d[37]), "+f"(d[38]), "+f"(d[39])
      : "r"(da), "n"(HA), "r"(db), "n"(HB), "r"(sc));
  }
};
template <> struct WgSST<192> {
  template <uint32_t HA, uint32_t HB>
  static __device__ __forceinline__ void mma(float* d, uint32_t da, uint32_t db, int sc) {
    asm volatile("{\n.reg .pred p;\n.reg .b64 da, db;\nsetp.ne.b32 p, %100, 0;\n"
      "mov.b64 da, {%96, %97};\nmov.b64 db, {%98, %99};\n"
      "wgmma.mma_async.sync.aligned.m64n192k16.f32.bf16.bf16 {"
      "%0, %1, %2, %3, %4, %5, %6, %7, %8, %9, %10, %11, %12, %13, %14, %15, "
      "%16, %17, %18, %19, %20, %21, %22, %23, %24, %25, %26, %27, %28, %29, %30, %31, "
      "%32, %33, %34, %35, %36, %37, %38, %39, %40, %41, %42, %43, %44, %45, %46, %47, "
      "%48, %49, %50, %51, %52, %53, %54, %55, %56, %57, %58, %59, %60, %61, %62, %63, "
      "%64, %65, %66, %67, %68, %69, %70, %71, %72, %73, %74, %75, %76, %77, %78, %79, "
      "%80, %81, %82, %83, %84, %85, %86, %87, %88, %89, %90, %91, %92, %93, %94, %95"
      "}, da, db, p, 1, 1, 0, 1;\n}\n"
      : "+f"(d[0]), "+f"(d[1]), "+f"(d[2]), "+f"(d[3]), "+f"(d[4]), "+f"(d[5]), "+f"(d[6]), "+f"(d[7]),
        "+f"(d[8]), "+f"(d[9]), "+f"(d[10]), "+f"(d[11]), "+f"(d[12]), "+f"(d[13]), "+f"(d[14]), "+f"(d[15]),
        "+f"(d[16]), "+f"(d[17]), "+f"(d[18]), "+f"(d[19]), "+f"(d[20]), "+f"(d[21]), "+f"(d[22]), "+f"(d[23]),
        "+f"(d[24]), "+f"(d[25]), "+f"(d[26]), "+f"(d[27]), "+f"(d[28]), "+f"(d[29]), "+f"(d[30]), "+f"(d[31]),
        "+f"(d[32]), "+f"(d[33]), "+f"(d[34]), "+f"(d[35]), "+f"(d[36]), "+f"(d[37]), "+f"(d[38]), "+f"(d[39]),
        "+f"(d[40]), "+f"(d[41]), "+f"(d[42]), "+f"(d[43]), "+f"(d[44]), "+f"(d[45]), "+f"(d[46]), "+f"(d[47]),
        "+f"(d[48]), "+f"(d[49]), "+f"(d[50]), "+f"(d[51]), "+f"(d[52]), "+f"(d[53]), "+f"(d[54]), "+f"(d[55]),
        "+f"(d[56]), "+f"(d[57]), "+f"(d[58]), "+f"(d[59]), "+f"(d[60]), "+f"(d[61]), "+f"(d[62]), "+f"(d[63]),
        "+f"(d[64]), "+f"(d[65]), "+f"(d[66]), "+f"(d[67]), "+f"(d[68]), "+f"(d[69]), "+f"(d[70]), "+f"(d[71]),
        "+f"(d[72]), "+f"(d[73]), "+f"(d[74]), "+f"(d[75]), "+f"(d[76]), "+f"(d[77]), "+f"(d[78]), "+f"(d[79]),
        "+f"(d[80]), "+f"(d[81]), "+f"(d[82]), "+f"(d[83]), "+f"(d[84]), "+f"(d[85]), "+f"(d[86]), "+f"(d[87]),
        "+f"(d[88]), "+f"(d[89]), "+f"(d[90]), "+f"(d[91]), "+f"(d[92]), "+f"(d[93]), "+f"(d[94]), "+f"(d[95])
      : "r"(da), "n"(HA), "r"(db), "n"(HB), "r"(sc));
  }
};

struct FftConst {
  uint32_t f[2][4], fi[4][4];
  float ta[4], tb[4];
};
__device__ __forceinline__ void cis(int m, float scale, float& c, float& s) {
  const float a = (float)m * (-6.283185307179586f * scale);
  c = __cosf(a);
  s = __sinf(a);
}
__device__ __forceinline__ void fft_tables(uint32_t (&v)[12], int tw) {
  const int row = tw >> 2, ch = tw & 3;
#pragma unroll
  for (int i = 0; i < 4; i++) {
    float c[2], s[2], x[2];
#pragma unroll
    for (int e = 0; e < 2; e++) {
      cis((((32 * (8 * ch + 2 * i + e) + 15) * (4 * row - 63) + 2048) & 4095) - 2048, 1.f / 4096, c[e], s[e]);
      float gc, gs;
      cis((((row & 15) * (8 * (ch & 1) + 2 * i + e) + 8) & 15) - 8, 1.f / 16, gc, gs);
      x[e] = (row >> 4) == (ch >> 1) ? gc : (ch >> 1) ? gs : -gs;
    }
    v[i] = pack2(c[0] * 0.125f, c[1] * 0.125f);
    v[4 + i] = pack2(s[0] * 0.125f, s[1] * 0.125f);
    v[8 + i] = pack2(x[0], x[1]);
  }
#pragma unroll
  for (int i = 0; i < 12; i++) asm volatile("" : "+r"(v[i]));
}
__device__ __forceinline__ void fft_tables_store(const uint32_t (&v)[12], uint32_t sb, int tw) {
  const int row = tw >> 2;
  const uint32_t x = ((tw ^ (row >> 1)) & 3) << 4, a = sb + OFF_FT + (16 * (row >> 3) + (row & 7)) * 64 + x;
  sts128(a, v[0], v[1], v[2], v[3]);
  sts128(a + 512, v[4], v[5], v[6], v[7]);
  sts128(sb + OFF_GT + row * 64 + x, v[8], v[9], v[10], v[11]);
}
__device__ __forceinline__ void fft_twiddles(FftConst& k, int w, int lane) {
#pragma unroll
  for (int i = 0; i < 4; i++) {
    float c, s;
    cis((2 * (8 * (i >> 1) + 2 * (lane & 3) + (i & 1)) - 15) * (4 * (8 * w + (lane >> 2)) - 63), 1.f / 4096, c, s);
    k.ta[i] = __fdividef(-s, 1.f + c);
    k.tb[i] = s;
  }
  pin<4>(k.ta);
  pin<4>(k.tb);
}
__device__ __forceinline__ void fft_matrices(FftConst& k, uint32_t sb, int w, int lane) {
  const uint32_t x = (lane >> 1) & 3;
#pragma unroll
  for (int i = 0; i < 2; i++) {
    ldsm4(k.f[i], sb + OFF_FT + (16 * w + (lane & 15)) * 64 + (((2 * i + (lane >> 4)) ^ x) << 4));
    ldsm4t(k.fi[i], sb + OFF_FT + (32 * i + lane) * 64 + ((w ^ x) << 4));
#pragma unroll
    for (int j = 0; j < 4; j++) {
      k.fi[2 + i][j] = (j & 1) ? k.fi[i][j - 1] ^ 0x80008000u : k.fi[i][j + 1];
      asm volatile("" : "+r"(k.fi[2 + i][j]));
    }
  }
}
template <bool INV> __device__ __forceinline__ void rot(float& x, float& y, float a, float b) {
  x = fmaf(INV ? -a : a, y, x);
  y = fmaf(INV ? -b : b, x, y);
  x = fmaf(INV ? -a : a, y, x);
}
__device__ __forceinline__ void twiddle_fwd(uint32_t (&a)[4][4], float* d, const FftConst& k) {
#pragma unroll
  for (int q = 0; q < 4; q++)
#pragma unroll
    for (int j = 0; j < 2; j++) {
      float* x = d + 8 * q + 4 * j;
      rot<false>(x[0], x[2], k.ta[2 * j], k.tb[2 * j]);
      rot<false>(x[1], x[3], k.ta[2 * j + 1], k.tb[2 * j + 1]);
      a[q & 2][2 * j + (q & 1)] = pack2(x[0], x[1]);
      a[(q & 2) + 1][2 * j + (q & 1)] = pack2(x[2], x[3]);
    }
}
__device__ __forceinline__ void g_step(float* d, const uint32_t (&a)[4][4], uint32_t dre, uint32_t dim) {
  WgRS<32>::set<HI_SW64>(d, a[0], dre);
  WgRS<32>::set<HI_SW64>(d + 16, a[2], dre);
  WgRS<32>::mma<HI_SW64>(d, a[1], dim);
  WgRS<32>::mma<HI_SW64>(d + 16, a[3], dim);
  wg_commit();
}

__device__ __forceinline__ void conv_channel(const FftConst& k, uint32_t sb, int c, int wg, int w, int lane) {
  const uint32_t cb = sb + off_ch(c), bars = sb + OFF_BAR;
  const uint32_t du = desc_lo(cb, 1024), dg = desc_lo(sb + OFF_GT, 16), dz = desc_lo(cb + U_BYTES, 16);
  float U[32], H[32];
  uint32_t a[4][4], e[4][4];
  const float dv = __uint_as_float(lds32(sb + OFF_D + 4 * c));
  wg_fence();
  WgRS<64>::set<HI_SW32>(H, k.f[0], du + 256);
  WgRS<64>::mma<HI_SW32>(H, k.f[1], du + 256 + 32);
  wg_commit();
  wg_wait<0>();
  pin<32>(H);
  twiddle_fwd(a, H, k);
  if (ATT_GATE && H_EARLY) mbar_wait(bars + 8 * B_ATTN, 0);
  mbar_wait(bars + 8 * (B_U + (c < 3 ? c : 3)), 0);
  TSM(w == 0 && c < 3, 7 + wg);
  if (TOK_G < 8 && c > 0) mbar_wait(bars + 8 * (B_TOK + c - 1), 0);
  wg_fence();
  WgRS<64>::set<HI_SW32>(U, k.f[0], du);
  WgRS<64>::mma<HI_SW32>(U, k.f[1], du + 32);
  wg_commit();
  g_step(H, a, dg, dg + 64);
  wg_wait<1>();
  pin<32>(U);
  if (TOK_G == 1 && lane == 0) mbar_arrive(bars + 8 * (B_TOK + c));
  twiddle_fwd(e, U, k);
  wg_fence();
  g_step(U, e, dg, dg + 64);
  if (TOK_G == 2 && lane == 0) mbar_arrive(bars + 8 * (B_TOK + c));
  wg_wait<0>();
  pin<32>(U);
  pin<32>(H);
#pragma unroll
  for (int j = 0; j < 2; j++) {
    float pr[4][2], pi[4][2];
#pragma unroll
    for (int x = 0; x < 2; x++) {
      H[4 * j + x] += dv;
#pragma unroll
      for (int m = 0; m < 4; m++) {
#pragma unroll
        for (int q = 0; q <= m; q++) {
          const int ih = 16 * (q >> 1) + 2 * (q & 1) + 4 * j + x, iu = 16 * ((m - q) >> 1) + 2 * ((m - q) & 1) + 4 * j + x;
          pr[m][x] = q ? fmaf(H[ih], U[iu], pr[m][x]) : H[ih] * U[iu];
          pi[m][x] = q ? fmaf(H[ih], U[iu + 8], pi[m][x]) : H[ih] * U[iu + 8];
          pr[m][x] = fmaf(-H[ih + 8], U[iu + 8], pr[m][x]);
          pi[m][x] = fmaf(H[ih + 8], U[iu], pi[m][x]);
        }
      }
    }
#pragma unroll
    for (int m = 0; m < 4; m++) {
      a[m & 2][2 * j + (m & 1)] = pack2(pr[m][0], pr[m][1]);
      a[(m & 2) + 1][2 * j + (m & 1)] = pack2(pi[m][0], pi[m][1]);
    }
  }
  wg_fence();
  g_step(U, a, dg + 64, dg);
  if (TOK_G == 3 && lane == 0) mbar_arrive(bars + 8 * (B_TOK + c));
  const uint32_t za = cb + U_BYTES + (8 * w + (lane & 7)) * 128 + (((lane >> 3) ^ (lane & 7)) << 4);
  const uint32_t ya = cb + (lane >> 4) * 1024 + (8 * w + (lane & 7)) * 32 + ((((lane >> 3) ^ (lane >> 2)) & 1) << 4);
  wg_sync(1 + wg);
  wg_wait<0>();
  pin<32>(U);
  TSIF(w == 0, 80 + c);
#pragma unroll
  for (int p = 0; p < 2; p++) {
#pragma unroll
    for (int i = 0; i < 4; i++) {
      const int j = i & 1;
      float* x = U + 16 * p + 4 * j + (i & 2);
      rot<true>(x[8], x[0], k.ta[2 * j], k.tb[2 * j]);
      rot<true>(x[9], x[1], k.ta[2 * j + 1], k.tb[2 * j + 1]);
      e[p][i] = pack2(x[8], x[9]);
      e[2 + p][i] = pack2(x[0], x[1]);
    }
    stsm4(za ^ (64 * p), e[p]);
    stsm4((za ^ (64 * p)) + 4096, e[2 + p]);
  }
  fence_async_smem();
  wg_sync(1 + wg);
  wg_fence();
  WgRS<64>::set<HI_SW128>(H, k.fi[0], dz);
#pragma unroll
  for (int ks = 1; ks < 4; ks++) WgRS<64>::mma<HI_SW128>(H, k.fi[ks], dz + 128 * ks);
  wg_commit();
  wg_wait<0>();
  pin<32>(H);
  TSIF(w == 0, 88 + c);
#pragma unroll
  for (int j = 0; j < 8; j++)
    a[j >> 2][j & 3] = j < 2 ? pack2(H[4 * j], H[4 * j + 1]) : pack2(H[4 * j] + H[4 * j - 6], H[4 * j + 1] + H[4 * j - 5]);
  stsm4(ya, a[0]);
  stsm4(ya + 2048, a[1]);
  fence_async_smem();
  __syncwarp();
}

__device__ __forceinline__ void prep_slab(uint4* res, const uint2* sw, uint32_t sb, int slab, int w, int lane) {
  const int t = lane & 3, tp = (lane & 7) >> 1, pos = 8 * tp + 2 * (((lane >> 3) + tp) & 3) + (lane & 1);
  const uint32_t base = sb + OFF_KVS + slab * KVS_BYTES + pos * 128;
  uint32_t kk[2][4][4], vv[2][4];
  mbar_wait(sb + OFF_BAR + 8 * (B_KV + slab), 0);
#pragma unroll
  for (int h = 0; h < 2; h++) {
#pragma unroll
    for (int j = 0; j < 4; j++) {
      const uint32_t a = base + 128 * j;
      ldsm4t(kk[h][j], a + (((w + 4 * h) ^ ((a >> 7) & 7)) << 4));
    }
    const uint32_t a = base + KVS_V;
    ldsm4t(vv[h], a + (((w + 4 * h) ^ ((a >> 7) & 7)) << 4));
  }
#pragma unroll
  for (int h = 0; h < 2; h++) {
    uint32_t (&k)[4][4] = kk[h];
    uint32_t (&v)[4] = vv[h];
    const uint32_t w0 = __byte_perm(sw[h].x, 0, 0x1010), w1 = __byte_perm(sw[h].x, 0, 0x3232);
    const uint32_t w2 = __byte_perm(sw[h].y, 0, 0x1010), w3 = __byte_perm(sw[h].y, 0, 0x3232);
#pragma unroll
    for (int m = 0; m < 4; m++)
      v[m] = bmul(badd(badd(badd(bmul(k[0][m], w3), bmul(k[1][m], w2)), bmul(k[2][m], w1)), bmul(k[3][m], w0)), v[m]);
    uint32_t a[4];
#pragma unroll
    for (int m = 0; m < 4; m++) a[m] = (t & 1) ? v[(m + 3) & 3] : v[m];
    res[h] = (t & 2) ? make_uint4(a[2], a[3], a[0], a[1]) : make_uint4(a[0], a[1], a[2], a[3]);
  }
}

__device__ __forceinline__ void prep_gate(const Params& p, int b, int w, int lane) {
  uint2 gw[5], x[4][5];
#pragma unroll
  for (int j = 0; j < 5; j++) gw[j] = ldg64(reinterpret_cast<const uint2*>(p.gate_w) + lane + 32 * j);
#pragma unroll
  for (int i = 0; i < 4; i++)
#pragma unroll
    for (int j = 0; j < 5; j++)
      x[i][j] = ldg64(reinterpret_cast<const uint2*>(p.q) + (16 * b + 4 * w + i) * (DIM / 4) + lane + 32 * j);
  float s[4];
#pragma unroll
  for (int i = 0; i < 4; i++) {
    s[i] = 0.f;
#pragma unroll
    for (int j = 0; j < 5; j++) {
      const uint32_t m0 = bmul(x[i][j].x, gw[j].x), m1 = bmul(x[i][j].y, gw[j].y);
      s[i] += (bf_lo(m0) + bf_hi(m0)) + (bf_lo(m1) + bf_hi(m1));
    }
  }
  const bool h = lane & 16, q = lane & 8;
  const float a = (h ? s[2] : s[0]) + __shfl_xor_sync(0xffffffffu, h ? s[0] : s[2], 16);
  const float c = (h ? s[3] : s[1]) + __shfl_xor_sync(0xffffffffu, h ? s[1] : s[3], 16);
  float z = (q ? c : a) + __shfl_xor_sync(0xffffffffu, q ? a : c, 8);
#pragma unroll
  for (int o = 4; o > 0; o >>= 1) z += __shfl_xor_sync(0xffffffffu, z, o);
  z = bf_lo(pack2(z, 0.f));
  if ((lane & 7) == 0) g_gate[16 * b + 4 * w + (lane >> 3)] = bf_lo(pack2(__fdividef(1.f, 1.f + __expf(-z)), 0.f));
}

__device__ __forceinline__ uint32_t bmax(uint32_t a, uint32_t b) {
  uint32_t d;
  asm("max.bf16x2 %0, %1, %2;" : "=r"(d) : "r"(a), "r"(b));
  return d;
}
__device__ __forceinline__ void softmax_two(const float (&l)[2][2], uint32_t& p0, uint32_t& p1) {
  constexpr float kScale = 0.22360679774997896f, kLog2e = 1.4426950408889634f;
  const uint32_t r0 = pack2(l[0][0], l[1][0]), r1 = pack2(l[0][1], l[1][1]);
  const uint32_t x0 = pack2(bf_lo(r0) * kScale, bf_hi(r0) * kScale), x1 = pack2(bf_lo(r1) * kScale, bf_hi(r1) * kScale);
  uint32_t m = bmax(x0, x1);
  m = bmax(m, __shfl_xor_sync(0xffffffffu, m, 1));
  m = bmax(m, __shfl_xor_sync(0xffffffffu, m, 2));
  const float m0 = bf_lo(m) * kLog2e, m1 = bf_hi(m) * kLog2e;
  p0 = pack2(ex2(bf_lo(x0) * kLog2e - m0), ex2(bf_lo(x1) * kLog2e - m0));
  p1 = pack2(ex2(bf_hi(x0) * kLog2e - m1), ex2(bf_hi(x1) * kLog2e - m1));
}

__device__ __forceinline__ void halo_read(uint32_t (&kpv)[10], uint32_t (&vpv)[10], uint32_t (&tg)[7], const uint4* hp) {
#pragma unroll
  for (int j = 0; j < 7; j++) {
    uint32_t x0, x1, x2;
    asm volatile("ld.relaxed.gpu.global.v4.u32 {%0, %1, %2, %3}, [%4];"
                 : "=r"(x0), "=r"(x1), "=r"(x2), "=r"(tg[j]) : "l"(hp + 32 * j) : "memory");
    if (j < 4) kpv[3 * j] = x0; else vpv[3 * j - 10] = x0;
    if (j < 3) kpv[3 * j + 1] = x1; else vpv[3 * j - 9] = x1;
    if (j < 3) kpv[3 * j + 2] = x2; else if (j < 6) vpv[3 * j - 8] = x2;
  }
}

template <int ROT>
__device__ __forceinline__ void pack_qkv(const float* acc, uint32_t (&qlo)[10], uint32_t (&qhi)[10], uint32_t (&klo)[10],
                                         uint32_t (&khi)[10], uint32_t (&vlo)[10], uint32_t (&vhi)[10]) {
#pragma unroll
  for (int j = 0; j < 10; j++) {
    const int x = (j + ROT) % 10, tq = x < 8 ? x : 16 + x, tk = x < 8 ? 8 + x : 18 + x, tv = x < 8 ? 16 + x : 20 + x;
    khi[j] = pack2(acc[4 * tk + 2], acc[4 * tk + 3]);
    vhi[j] = movm(pack2(acc[4 * tv + 2], acc[4 * tv + 3]));
    qlo[j] = pack2(acc[4 * tq], acc[4 * tq + 1]);
    qhi[j] = pack2(acc[4 * tq + 2], acc[4 * tq + 3]);
    klo[j] = pack2(acc[4 * tk], acc[4 * tk + 1]);
    vlo[j] = pack2(acc[4 * tv], acc[4 * tv + 1]);
    asm volatile("" : "+r"(khi[j]), "+r"(qlo[j]), "+r"(qhi[j]), "+r"(klo[j]), "+r"(vlo[j]));
  }
}

__device__ __forceinline__ void attention(float* acc, uint32_t sb, int b, int par, int w, int lane) {
  const int g = lane >> 2, t = lane & 3;
  uint32_t klo[10], khi[10], vlo[10], vhi[10], qlo[10], qhi[10], kpv[10], vpv[10];
  if (tail_first(b & 7)) pack_qkv<8>(acc, qlo, qhi, klo, khi, vlo, vhi);
  else pack_qkv<0>(acc, qlo, qhi, klo, khi, vlo, vhi);
  uint32_t tag = 0;
  if (w == 0 || w == 3) {
    mbar_wait(sb + OFF_BAR + 8 * B_EPOCH, 0);
    tag = lds32(sb + OFF_EPOCH) + 1;
  }
  const uint32_t xa = sb + OFF_KVX + (par * 3) * 2560 + lane * 16;
  if (w < 3) {
    mbar_wait(sb + OFF_BAR + 8 * B_S3, 0);
    sts128(xa + w * 2560, khi[0], khi[1], khi[2], khi[3]);
    sts128(xa + w * 2560 + 512, khi[4], khi[5], khi[6], khi[7]);
    sts128(xa + w * 2560 + 1024, khi[8], khi[9], vhi[0], vhi[1]);
    sts128(xa + w * 2560 + 1536, vhi[2], vhi[3], vhi[4], vhi[5]);
    sts128(xa + w * 2560 + 2048, vhi[6], vhi[7], vhi[8], vhi[9]);
  } else if (b < NCTA - 8) {
    uint4* ho = g_halo + (b * 2 + par) * 224 + lane;
#pragma unroll
    for (int j = 0; j < 7; j++) {
      const uint32_t x0 = j < 4 ? khi[3 * j] : vhi[3 * j - 10], x1 = j < 3 ? khi[3 * j + 1] : vhi[3 * j - 9];
      const uint32_t x2 = j < 3 ? khi[3 * j + 2] : j < 6 ? vhi[3 * j - 8] : 0u;
      asm volatile("st.relaxed.gpu.global.v4.u32 [%0], {%1, %2, %3, %4};" ::"l"(ho + 32 * j), "r"(x0), "r"(x1), "r"(x2), "r"(tag) : "memory");
    }
  }
  TSIF(par == 0 && w == 1, 64);
  TSIF(par == 0 && w == 3, 76);
#pragma unroll
  for (int j = 0; j < 10; j++) vlo[j] = movm(vlo[j]);
  const bool far0 = 2 * t > g, far1 = 2 * t + 1 > g;
  const uint32_t mfar = (far0 ? 0x0000FFFFu : 0u) | (far1 ? 0xFFFF0000u : 0u);
  float slo[4][2], shi[4][2], lg[2][2];
  uint32_t phi[4], plo[4], qml[4], qmh[4];
#pragma unroll
  for (int h = 0; h < 4; h++) {
    const int f = h == 0 ? 0 : h == 1 ? 3 : h == 2 ? 5 : 8, hf = h < 2 ? 2 : 7;
    const bool mine = (h & 1) ? t >= 2 : t < 2;
    qml[h] = mine ? qlo[hf] : 0u;
    qmh[h] = mine ? qhi[hf] : 0u;
    float a[4] = {0.f, 0.f, 0.f, 0.f}, c[4] = {0.f, 0.f, 0.f, 0.f};
    mma16816(a, qlo[f], qhi[f], qlo[f + 1], qhi[f + 1], klo[f], klo[f + 1]);
    mma16816(c, qlo[f], qhi[f], qlo[f + 1], qhi[f + 1], khi[f], khi[f + 1]);
    mma1688(a, qml[h], qmh[h], klo[hf]);
    mma1688(c, qml[h], qmh[h], khi[hf]);
    slo[h][0] = a[0];
    slo[h][1] = a[1];
    shi[h][0] = lg[h & 1][0] = far0 ? a[2] : c[2];
    shi[h][1] = lg[h & 1][1] = far1 ? a[3] : c[3];
    if (!ATT_MERGE && (h & 1)) softmax_two(lg, phi[h - 1], phi[h]);
  }
  TSIF(par == 0 && w == 1, 65);
  wg_sync(1 + par);
  TSIF(par == 0 && w == 1, 66);
  const bool nohist = (w == 0) && (b < 8);
  const uint4* hp = g_halo + ((b - 8) * 2 + par) * 224 + lane;
  uint32_t tg[7];
  if (w > 0) {
    const uint4 v0 = lds128(xa + (w - 1) * 2560), v1 = lds128(xa + (w - 1) * 2560 + 512), v2 = lds128(xa + (w - 1) * 2560 + 1024);
    const uint4 v3 = lds128(xa + (w - 1) * 2560 + 1536), v4 = lds128(xa + (w - 1) * 2560 + 2048);
    kpv[0] = v0.x; kpv[1] = v0.y; kpv[2] = v0.z; kpv[3] = v0.w; kpv[4] = v1.x; kpv[5] = v1.y; kpv[6] = v1.z; kpv[7] = v1.w;
    kpv[8] = v2.x; kpv[9] = v2.y; vpv[0] = v2.z; vpv[1] = v2.w; vpv[2] = v3.x; vpv[3] = v3.y; vpv[4] = v3.z; vpv[5] = v3.w;
    vpv[6] = v4.x; vpv[7] = v4.y; vpv[8] = v4.z; vpv[9] = v4.w;
  } else if (nohist) {
#pragma unroll
    for (int j = 0; j < 10; j++) kpv[j] = vpv[j] = 0u;
  } else {
    TSIF(par == 0, 77);
    halo_read(kpv, vpv, tg, hp);
  }
  if (w == 0 && !nohist) {
    int spins = 0;
    while (true) {
      bool ok = true;
#pragma unroll
      for (int j = 0; j < 7; j++) ok = ok && tg[j] == tag;
      if (__all_sync(0xffffffffu, ok) || ++spins > SPIN_LIMIT) break;
      halo_read(kpv, vpv, tg, hp);
    }
    TSIF(par == 0, 79);
  }
#pragma unroll
  for (int h = 0; h < 4; h++) {
    const int f = h == 0 ? 0 : h == 1 ? 3 : h == 2 ? 5 : 8, hf = h < 2 ? 2 : 7;
    float a[4] = {0.f, 0.f, 0.f, 0.f};
    mma16816(a, qlo[f], qhi[f], qlo[f + 1], qhi[f + 1], kpv[f], kpv[f + 1]);
    mma1688(a, qml[h], qmh[h], kpv[hf]);
    const float ninf = __int_as_float(0xff800000);
    lg[h & 1][0] = far0 ? (nohist ? ninf : a[0]) : slo[h][0];
    lg[h & 1][1] = far1 ? (nohist ? ninf : a[1]) : slo[h][1];
    if (h & 1) {
      softmax_two(lg, plo[h - 1], plo[h]);
      if (ATT_MERGE) {
        const float lh[2][2] = {{shi[h - 1][0], shi[h - 1][1]}, {shi[h][0], shi[h][1]}};
        softmax_two(lh, phi[h - 1], phi[h]);
      }
    }
  }
  TSIF(par == 0 && w <= 1, 67 + w);
  uint32_t ov[20];
#pragma unroll
  for (int hp = 0; hp < 2; hp++) {
    const int hf = hp ? 7 : 2;
    float sh[4] = {0.f, 0.f, 0.f, 0.f}, i0 = 0.f, i1 = 0.f;
#pragma unroll
    for (int e = 0; e < 2; e++) {
      const int h = 2 * hp + e, f = h == 0 ? 0 : h == 1 ? 3 : h == 2 ? 5 : 8;
      const uint32_t a0 = plo[h] & mfar, a2 = plo[h] & ~mfar, a3 = phi[h] & mfar, c1 = phi[h] & ~mfar;
      float sum[4] = {0.f, 0.f, 0.f, 0.f};
      mma1688(sum, plo[h], phi[h], 0x3F803F80u);
      const float r0 = rcp(sum[0]), r1 = rcp(sum[2]);
#pragma unroll
      for (int j = f; j < f + 2; j++) {
        float o[4] = {0.f, 0.f, 0.f, 0.f};
        mma16816(o, a0, 0u, a2, a3, vpv[j], vlo[j]);
        mma1688(o, 0u, c1, vhi[j]);
        ov[2 * j] = pack2(o[0] * r0, o[1] * r0);
        ov[2 * j + 1] = pack2(o[2] * r1, o[3] * r1);
      }
      const bool mine = e ? g >= 4 : g < 4;
      mma16816(sh, a0, 0u, a2, a3, mine ? vpv[hf] : 0u, mine ? vlo[hf] : 0u);
      mma1688(sh, 0u, c1, mine ? vhi[hf] : 0u);
      if (e == 0 || t >= 2) {
        i0 = r0;
        i1 = r1;
      }
    }
    ov[2 * hf] = pack2(sh[0] * i0, sh[1] * i0);
    ov[2 * hf + 1] = pack2(sh[2] * i1, sh[3] * i1);
  }
  TS(32 + 4 * par + w);
  mbar_wait(sb + OFF_BAR + 8 * B_P1, 0);
  const uint32_t oa = sb + OFF_OA + (lane >> 4) * 2048 + (32 * w + 2 * (lane & 15) + par) * 16;
#pragma unroll
  for (int j = 0; j < 5; j++) stsm4(oa + 4096 * j, ov + 4 * j);
  TSIF(par == 0 && w == 0, 120);
  fence_async_smem();
  TSIF(par == 0 && w == 0, 121);
  __syncwarp();
  if (lane == 0) mbar_arrive(sb + OFF_BAR + 8 * B_ATTN);
  TSIF(par == 0 && w == 0, 122);
}

struct Maps {
  CUtensorMap x, wm, wt, k, v, y, wo, qm, qt, om, ot;
};

__device__ __forceinline__ void load_stage(uint32_t sb, int kb, int b, const Maps& m) {
  const uint32_t st = sb + (kb & 3) * STAGE_BYTES, bar = sb + OFF_BAR + 8 * (B_FULL1 + (kb & 3));
  const int r = b >> 3, hg = b & 7, slab = kb - KV_KB;
  const bool kv = slab >= 0 && slab < 5;
  const uint32_t kbar = sb + OFF_BAR + 8 * (B_KV + slab), dst = sb + OFF_KVS + slab * KVS_BYTES;
  mbar_expect_tx(bar, STAGE_BYTES);
  if (kv) mbar_expect_tx(kbar, KVS_BYTES);
  tma_3d(st, &m.x, 64 * kb, 64 * r, 0, bar);
  if (kv && KV_MIX) tma_3d(dst, &m.k, 0, 32 * (b >> 1) - 3, 2 * slab + (b & 1), kbar);
  tma_3d(st + ST_W, &m.wm, 80 * hg + (tail_first(hg) ? 16 : 0), 64 * kb, 0, bar);
  if (kv && KV_MIX) tma_3d(dst + KVS_V, &m.v, 0, 32 * (b >> 1), 2 * slab + (b & 1), kbar);
  tma_3d(st + ST_WT, &m.wt, 80 * hg + (tail_first(hg) ? 0 : 64), 64 * kb, 0, bar);
  if (kv && !KV_MIX) tma_3d(dst, &m.k, 0, 32 * (b >> 1) - 3, 2 * slab + (b & 1), kbar);
  if (kv && !KV_MIX) tma_3d(dst + KVS_V, &m.v, 0, 32 * (b >> 1), 2 * slab + (b & 1), kbar);
}

__global__ void __launch_bounds__(NTHR, 1) fused_kernel(const __grid_constant__ Maps m, const Params p) {
  extern __shared__ __align__(1024) uint8_t smem[];
  const uint32_t sb = (uint32_t)__cvta_generic_to_shared(smem);
  const uint32_t bars = sb + OFF_BAR;
  const int tid = threadIdx.x, lane = tid & 31;
  int b = blockIdx.x;
  if (BMAP == 1) b = (((b & 63) >> 3) * 2 + (b & 1)) * 8 + (((b < 64 ? 0x6521 : 0x7430) >> (4 * ((b >> 1) & 3))) & 7);
  if (BMAP == 2) b = ((b & 63) >> 2) * 8 + (((b < 64 ? 0x6521 : 0x7430) >> (4 * (b & 3))) & 7);
  if (BMAP == 3) b = (((b & 63) >> 3) * 2 + (b & 1)) * 8 + (((b < 64 ? 0x7430 : 0x6521) >> (4 * ((b >> 1) & 3))) & 7);
  if (BMAP == 4) b = (((b >> 4) * 2 + (b & 1)) * 8) + ((b >> 1) & 7);
  if (BMAP == 5) b = 127 - b;
  const int r = b >> 3, hg = b & 7;

  if (tid == T_ISSUE) {
    TSM(true, 0);
#pragma unroll
    for (int i = 0; i < 4; i++) mbar_init(bars + 8 * (B_FULL1 + i), 1);
#pragma unroll
    for (int i = 0; i < 3; i++) mbar_init(bars + 8 * (B_KV + i), 1);
    fence_async_smem();
#pragma unroll 1
    for (int kb = 0; kb <= PRE2; kb++) load_stage(sb, kb, b, m);
  } else if (tid >= T_PF && tid < T_PF + 11) {
    tm_prefetch(&m.x + (tid - T_PF));
  } else if (tid == T_INIT) {
#pragma unroll
    for (int i = 0; i < 4; i++) mbar_init(bars + 8 * (B_EMPTY1 + i), 8);
#pragma unroll
    for (int i = 0; i < 8; i++) mbar_init(bars + 8 * (B_FULL2 + i), 1);
#pragma unroll
    for (int i = 0; i < 4; i++) mbar_init(bars + 8 * (B_EMPTY2 + i), 8);
#pragma unroll
    for (int i = 0; i < 4; i++) mbar_init(bars + 8 * (B_U + i), 1);
    mbar_init(bars + 8 * B_HA, 4);
    mbar_init(bars + 8 * B_GATE, 4);
    mbar_init(bars + 8 * B_HB, 1);
    mbar_init(bars + 8 * B_KVD, 4);
    mbar_init(bars + 8 * B_QF, 1);
    mbar_init(bars + 8 * B_ATTN, 8);
    mbar_init(bars + 8 * B_P1, 8);
    mbar_init(bars + 8 * B_C34, 1);
#pragma unroll
    for (int i = 0; i < 5; i++) mbar_init(bars + 8 * (B_YST + i), 4);
#pragma unroll
    for (int i = 0; i < 5; i++) mbar_init(bars + 8 * (B_TOK + i), 4);
    mbar_init(bars + 8 * B_YSIG, 1);
    mbar_init(bars + 8 * B_YFULL, 1);
    mbar_init(bars + 8 * B_EPOCH, 1);
    mbar_init(bars + 8 * B_PREP, 4);
    mbar_init(bars + 8 * B_USIG, 1);
    mbar_init(bars + 8 * B_WST, 1);
#pragma unroll
    for (int i = 3; i < 5; i++) mbar_init(bars + 8 * (B_KV + i), 1);
    mbar_init(bars + 8 * B_E3, 8);
    mbar_init(bars + 8 * B_LAST, 1);
    mbar_init(bars + 8 * B_OSIG, 1);
    mbar_init(bars + 8 * B_WOP, 1);
    fence_async_smem();
  }
  const int warp = __shfl_sync(0xffffffffu, tid >> 5, 0), wg = warp >> 2, w = warp & 3;
  __syncthreads();

  if (wg == 3) {
    asm volatile("setmaxnreg.dec.sync.aligned.u32 56;");
    if (w == 0) {
      if (lane == 0) {
#pragma unroll 1
        for (int kb = 1 + PRE2; kb < 10; kb++) {
          if (kb >= 4) mbar_wait(bars + 8 * (kb == 7 ? B_E3 : B_EMPTY1 + (kb & 3)), (kb >> 3) & 1);
          TSIF(kb >= 4, 44 + kb);
          load_stage(sb, kb, b, m);
          if (kb == TRIG_KB) mbar_arrive(bars + 8 * B_LAST);
        }
        mbar_wait(bars + 8 * B_WOP, 0);
        mbar_wait(bars + 8 * WL_TRIG, 0);
        mbar_wait(bars + 8 * B_EPOCH, 0);
        flag_wait(g_cnt + C_W + 32 * hg, (lds32(sb + OFF_EPOCH) + 1) * 16);
        TS(30);
#pragma unroll 1
        for (int j = 0; j < 8; j++) {
          if (j >= 6) mbar_wait(bars + 8 * (B_EMPTY2 + j - 6), 0);
          if (j == 4) mbar_wait(bars + 8 * B_ATTN, 0);
          TSIF(j >= 6, 100 + j);
          if (RF_GATE && j == 6) mbar_wait(bars + 8 * B_YSIG, 0);
          mbar_expect_tx(bars + 8 * (B_FULL2 + j), j == 0 ? WO_BYTES : j == 5 ? O_BYTES + WO_BYTES + 512 : O_BYTES + WO_BYTES);
          bulk_load(sb + off_w(j), g_WO + (hg * 8 + step_src(hg, j)) * 800, WO_BYTES, bars + 8 * (B_FULL2 + j));
        }
        mbar_wait(bars + 8 * (B_EMPTY2 + 3), 0);
        mbar_expect_tx(bars + 8 * B_QF, O_BYTES);
        tma_2d(sb + OFF_QS, &m.qm, 80 * hg, 128 * r, bars + 8 * B_QF);
        tma_2d(sb + OFF_QT, &m.qt, 80 * hg + 64, 128 * r, bars + 8 * B_QF);
      }
    } else if (w == 1) {
      unsigned epoch = 0;
      if (lane == 0) {
        epoch = atomicAdd(g_cnt + C_LAUNCH, 1u) / NCTA;
        asm volatile("st.shared.u32 [%0], %1;" ::"r"(sb + OFF_EPOCH), "r"(epoch) : "memory");
        mbar_arrive(bars + 8 * B_EPOCH);
        mbar_wait(bars + 8 * B_KVD, 0);
        mbar_expect_tx(bars + 8 * B_HB, 5 * 4096);
#pragma unroll 1
        for (int c = 0; c < 5; c++) {
          if (c == 3) mbar_wait(bars + 8 * B_S3, 0);
          bulk_load(sb + off_ch(c) + U_BYTES, p.ssm_k + (5 * b + c) * SEQ, 4096, bars + 8 * B_HB);
        }
#pragma unroll
        for (int c = 0; c < 4; c++) mbar_expect_tx(bars + 8 * (B_U + c), c < 3 ? U_BYTES : 2 * U_BYTES);
        const uint4* usrc = g_U + 5 * b * U_PITCH;
        mbar_wait(bars + 8 * B_USIG, 0);
        flag_wait(g_cnt + C_PREP + 32 * (b & 15), (epoch + 1) * NCTA);
        TS(23);
#pragma unroll
        for (int c = 0; c < 5; c++) {
          if (c == 3) mbar_wait(bars + 8 * (B_U + 2), 0);
          bulk_load(sb + off_ch(c), usrc + c * U_PITCH, U_BYTES, bars + 8 * (B_U + (c < 3 ? c : 3)));
          TSIF(c == 0 || c == 4, 116 + (c >> 2));
        }
      }
      epoch = __shfl_sync(0xffffffffu, epoch, 0);
      if (lane < 8) {
        const int src = (b & ~7) | step_src(hg, lane);
        mbar_wait(bars + 8 * B_OSIG, 0);
        flag_wait(g_cnt + C_O + 32 * src, epoch + 1);
        if (lane >= 1 && lane < 4) bulk_load(sb + off_o(lane), g_O + src * 1280, O_BYTES, bars + 8 * (B_FULL2 + lane));
        __syncwarp(0xff);
        TS(21);
        if (lane == 5) bulk_load(sb + OFF_GATE, g_gate + 128 * r, 512, bars + 8 * (B_FULL2 + 5));
#pragma unroll 1
        for (int j = 4; j < 8; j++) {
          if (lane == j) {
            mbar_wait(bars + 8 * (j < 6 ? B_C34 : B_EMPTY2 + j - 6), 0);
            if (RF_GATE && j == 6) mbar_wait(bars + 8 * B_YSIG, 0);
            bulk_load(sb + off_o(j), g_O + src * 1280, O_BYTES, bars + 8 * (B_FULL2 + j));
          }
          __syncwarp(0xff);
        }
        TS(22);
      }
    } else if (w == 2) {
      mbar_wait(bars + 8 * B_PREP, 0);
      flag_signal(g_cnt + C_PREP, 16, lane);
      TS(25);
      if (lane == 0) mbar_arrive(bars + 8 * B_USIG);
      mbar_wait(bars + 8 * B_GATE, 0);
      if ((NOMB & 1) && lane == 0) asm volatile("fence.release.gpu;" ::: "memory");
      mbar_wait(bars + 8 * B_ATTN, 0);
      if (lane == 0) {
        if (O_DEFER) mbar_wait(bars + 8 * (B_U + 3), 0);
        asm volatile("cp.async.bulk.global.shared::cta.bulk_group [%0], [%1], 20480;\ncp.async.bulk.commit_group;\n"
                     "cp.async.bulk.wait_group 0;\nfence.proxy.async.global;" ::"l"(g_O + b * 1280), "r"(sb + OFF_OA) : "memory");
      }
      TS(74);
      if (!(NOMB & 1)) flag_signal(g_cnt + C_O + 32 * b, 1, lane);
      else if (lane == 0) flag_bump(g_cnt + C_O + 32 * b);
      TS(26);
      if (lane == 0) mbar_arrive(bars + 8 * B_OSIG);

    } else {
      if (lane == 0) {
        uint4* dst = g_WO + (hg * 8 + (r >> 1)) * 800 + (r & 1) * 80;
        mbar_wait(bars + 8 * B_P1, 0);
        mbar_wait(bars + 8 * WB_TRIG, 0);
        mbar_expect_tx(bars + 8 * B_WST, WO_BYTES / 2);
        tma_3d(sb + OFF_WS, &m.wo, 0, 40 * r, 5 * hg, bars + 8 * B_WST);
        mbar_wait(bars + 8 * B_WST, 0);
        mbar_wait(bars + 8 * WO_TRIG, 0);
#pragma unroll 1
        for (int n = 0; n < 5; n++)
          asm volatile("cp.async.bulk.global.shared::cta.bulk_group [%0], [%1], 1280;" ::"l"(dst + 160 * n), "r"(sb + OFF_WS + 1280 * n) : "memory");
        asm volatile("cp.async.bulk.commit_group;\ncp.async.bulk.wait_group 0;\nfence.proxy.async.global;" ::: "memory");
        if (!(NOMB & 4)) asm volatile("fence.release.gpu;" ::: "memory");
        flag_bump(g_cnt + C_W + 32 * hg);
        mbar_arrive(bars + 8 * B_WOP);
        TS(71);
#pragma unroll 1
        for (int c = 0; c < 5; c++) {
          mbar_wait(bars + 8 * (B_YST + c), 0);
          asm volatile("cp.async.bulk.global.shared::cta.bulk_group [%0], [%1], 4096;\ncp.async.bulk.commit_group;"
                       ::"l"(g_Y + (5 * b + c) * Y_PITCH), "r"(sb + off_ch(c)) : "memory");
          if (c == 2) {
            asm volatile("cp.async.bulk.wait_group.read 0;" ::: "memory");
            mbar_arrive(bars + 8 * B_C34);
          }
        }
        asm volatile("cp.async.bulk.wait_group 0;\nfence.proxy.async.global;" ::: "memory");
        TS(75);
        if (!(NOMB & 2)) asm volatile("fence.release.gpu;" ::: "memory");
        flag_bump(g_cnt + C_Y + 32 * (b >> 4));
        TS(27);
        mbar_arrive(bars + 8 * B_YSIG);
        mbar_expect_tx(bars + 8 * B_YFULL, 20480);
        flag_wait(g_cnt + C_Y + 32 * hg, (lds32(sb + OFF_EPOCH) + 1) * 16);
        TS(24);
        tma_2d(sb + OFF_YT, &m.y, 128 * r, 80 * hg, bars + 8 * B_YFULL);
        tma_2d(sb + OFF_YT + 10240, &m.y, 128 * r + 64, 80 * hg, bars + 8 * B_YFULL);
      }
    }
  } else {
    asm volatile("setmaxnreg.inc.sync.aligned.u32 152;");
    if (wg < 2) {
      float acc[120];
#pragma unroll
      for (int i = 0; i < 120; i++) acc[i] = 0.f;
      const uint32_t da = desc_lo(sb + wg * 8192, 16), db = desc_lo(sb + ST_W, 8192), dc = desc_lo(sb + ST_WT, 2048);
      if (PW1) pin<120>(acc);
      if (PW1 == 2) mbar_wait(bars + 8 * B_FULL1, 0);
#pragma unroll 1
      for (int kb = 0; kb < 10; kb++) {
        mbar_wait(bars + 8 * (B_FULL1 + (kb & 3)), (kb >> 2) & 1);
        const uint32_t so = (kb & 3) * (STAGE_BYTES >> 4);
        wg_fence();
#pragma unroll
        for (int k = 0; k < 4; k++) {
          WgSST<192>::mma<HI_SW128, HI_SW128>(acc, da + so + 2 * k, db + so + 128 * k, 1);
          WgSST<48>::mma<HI_SW128, HI_SW32>(acc + 96, da + so + 2 * k, dc + so + 32 * k, 1);
        }
        wg_commit();
        wg_wait<1>();
        if (kb > 0 && lane == 0) mbar_arrive(bars + 8 * (kb == 4 ? B_E3 : B_EMPTY1 + ((kb - 1) & 3)));
      }
      wg_wait<0>();
      pin<120>(acc);
      if (lane == 0) mbar_arrive(bars + 8 * B_P1);
      TSM(w == 0, 3 + wg);
      attention(acc, sb, b, wg, w, lane);
    } else {
      const int tw = tid & 127, chl = 64 * (b & 1) + 8 * w + (lane >> 2);
      uint4* up = g_U + chl * U_PITCH + ((4 * (b >> 1) + (lane & 3)) ^ ((b >> 2) & 1));
      uint2 sw[10];
      uint32_t dv = 0;
      if (lane < 5) dv = __ldg(reinterpret_cast<const unsigned short*>(p.ssm_D) + 5 * b + lane);
#pragma unroll
      for (int i = 0; i < 10; i++) sw[i] = ldg64(reinterpret_cast<const uint2*>(p.shift_k) + chl + 128 * (i >> 1) + 32 * (i & 1));
      uint32_t tab[12];
      fft_tables(tab, tw);
      uint4 res[10];
#pragma unroll
      for (int i = 0; i < 10; i++) res[i] = make_uint4(0, 0, 0, 0);
#pragma unroll 1
      for (int slab = 0; slab < 5; slab++) {
#pragma unroll
        for (int i = 0; i < 8; i++) res[i] = res[i + 2];
        prep_slab(res + 8, sw, sb, slab, w, lane);
        TSIF(w == 0, 99 + 4 * slab);
#pragma unroll
        for (int i = 0; i < 8; i++) sw[i] = sw[i + 2];
      }
      TSIF(w == 0, 28);
      __syncwarp();
      if (lane == 0) mbar_arrive(bars + 8 * B_KVD + ((res[8].x ^ res[9].x) & p.zero));
      mbar_wait(bars + 8 * B_KVD, 0);
      fft_tables_store(tab, sb, tw);
      mbar_wait(bars + 8 * B_LAST, 0);
#pragma unroll
      for (int i = 0; i < 10; i++) up[(128 * (i >> 1) + 32 * (i & 1)) * U_PITCH] = res[i];
      __syncwarp();
      if (lane == 0) mbar_arrive(bars + 8 * B_PREP);
      TSIF(w == 0, 5);
      mbar_wait(bars + 8 * (G_AFTER ? B_USIG : B_LAST), 0);
      prep_gate(p, b, w, lane);
      __syncwarp();
      if (lane == 0) mbar_arrive(bars + 8 * B_GATE);
      TSIF(w == 0, 72);
      mbar_wait(bars + 8 * B_HB, 0);
      TSIF(w == 0, 123);
      const uint32_t ha = sb + U_BYTES + ((tw >> 3) * 16 + 8 + (tw & 7)) * 16;
      uint4 hv[5];
#pragma unroll
      for (int c = 0; c < 5; c++) hv[c] = lds128(ha + off_ch(c));
      __syncwarp();
#pragma unroll
      for (int c = 0; c < 5; c++) sts128((ha ^ 16) + off_ch(c), hv[c].x, hv[c].y, hv[c].z, hv[c].w);
      if (tw < 5) asm volatile("st.shared.f32 [%0], %1;" ::"r"(sb + OFF_D + 4 * tw), "f"(bf_lo(dv) * 0.125f) : "memory");
      fence_async_smem();
      __syncwarp();
      if (lane == 0) mbar_arrive(bars + 8 * B_HA);
      TSIF(w == 0, 6);
    }

    FftConst fc;
    fft_twiddles(fc, w, lane);
    mbar_wait(bars + 8 * B_HA, 0);
    fft_matrices(fc, sb, w, lane);
    if (ATT_GATE && !H_EARLY) mbar_wait(bars + 8 * B_ATTN, 0);
    TSIF(w == 0 && wg == 2, 124);
#pragma unroll 1
    for (int c = wg == 2 ? 0 : wg + 1; c < 5; c += 3) {
      conv_channel(fc, sb, c, wg, w, lane);
      if (lane == 0) mbar_arrive(bars + 8 * (B_YST + c));
      TSM(w == 0, 10 + c);
    }

    if (wg < 2) {
      const int g = lane >> 2;
      float acc[40];
#pragma unroll
      for (int i = 0; i < 40; i++) acc[i] = 0.f;
      const uint32_t da = desc_lo(sb + wg * 1024, 2048), db = desc_lo(sb, 2560);
      mbar_wait(bars + 8 * B_ATTN, 0);
      mbar_wait(bars + 8 * (B_YST + 3), 0);
      mbar_wait(bars + 8 * (B_YST + 4), 0);
      if (PW2) mbar_wait(bars + 8 * B_FULL2, 0);
#pragma unroll 1
      for (int j = 0; j < 8; j++) {
        mbar_wait(bars + 8 * (B_FULL2 + j), 0);
        const uint32_t oa = da + (off_o(j) >> 4), ob = db + (off_w(j) >> 4);
        wg_fence();
#pragma unroll
        for (int k = 0; k < 5; k++) WgSST<80>::mma<HI_NONE, HI_SW32>(acc, oa + 256 * k, ob + 32 * k, 1);
        wg_commit();
        wg_wait<1>();
        if (j >= 1 && j <= 4 && lane == 0) mbar_arrive(bars + 8 * (B_EMPTY2 + j - 1));
      }
      TSIF(w == 0 && wg == 0, 113);
      const int tr = 64 * wg + 16 * w + (lane & 15);
      const uint32_t fm = sb + OFF_QS + tr * 128, fx = (lane >> 4) ^ (tr & 7);
      const uint32_t ft = sb + OFF_QT + tr * 32 + (((lane >> 4) ^ (tr >> 2)) & 1) * 16;
      const float g0 = __uint_as_float(lds32(sb + OFF_GATE + (64 * wg + 16 * w + g) * 4));
      const float g1 = __uint_as_float(lds32(sb + OFF_GATE + (64 * wg + 16 * w + 8 + g) * 4));
      const uint32_t ga = pack2(g0, g0), gb = pack2(g1, g1);
      const uint32_t na = pack2(1.f - g0, 1.f - g0), nb = pack2(1.f - g1, 1.f - g1);

      wg_wait<0>();
      pin<40>(acc);
      TSM(w == 0, 17 + wg);
      uint32_t pb[20];
#pragma unroll
      for (int j = 0; j < 10; j++) {
        pb[2 * j] = bmul(na, pack2(acc[4 * j], acc[4 * j + 1]));
        pb[2 * j + 1] = bmul(nb, pack2(acc[4 * j + 2], acc[4 * j + 3]));
        asm volatile("" : "+r"(pb[2 * j]), "+r"(pb[2 * j + 1]));
      }
      const uint32_t ya = sb + OFF_YT + wg * 10240 + ((lane >> 4) * 8 + (lane & 7)) * 128 +
                          (((2 * w + (((lane >> 3) & 1) ^ wg)) ^ (lane & 7)) << 4);
      uint32_t qf[20];
      mbar_wait(bars + 8 * B_QF, 0);
#pragma unroll
      for (int j = 0; j < 5; j++) ldsm4(qf + 4 * j, j < 4 ? fm + ((fx ^ (2 * j)) << 4) : ft);
      mbar_wait(bars + 8 * B_YFULL, 0);
      TSIF(w == 0 && wg == 0, 19);
#pragma unroll
      for (int j = 0; j < 5; j++) {
        uint32_t y[4];
        ldsm4t(y, ya + 2048 * j);
#pragma unroll
        for (int i = 0; i < 4; i++) qf[4 * j + i] = badd(bmul((i & 1) ? gb : ga, bmul(qf[4 * j + i], y[i])), pb[4 * j + i]);
      }
#pragma unroll
      for (int j = 0; j < 5; j++) stsm4(j < 4 ? fm + ((fx ^ (2 * j)) << 4) : ft, qf + 4 * j);
      fence_async_smem();
      __syncwarp();
      if (lane == 0) {
        const int row = 64 * wg + 16 * w;
        asm volatile("cp.async.bulk.tensor.2d.global.shared::cta.bulk_group [%0, {%2, %3}], [%1];"
                     ::"l"(&m.om), "r"(sb + OFF_QS + row * 128), "r"(80 * hg), "r"(128 * r + row) : "memory");
        asm volatile("cp.async.bulk.tensor.2d.global.shared::cta.bulk_group [%0, {%2, %3}], [%1];"
                     ::"l"(&m.ot), "r"(sb + OFF_QT + row * 32), "r"(80 * hg + 64), "r"(128 * r + row) : "memory");
        asm volatile("cp.async.bulk.commit_group;\ncp.async.bulk.wait_group.read 0;" ::: "memory");
      }
      TSM(true, 40 + 4 * wg + w);
      if (ENDBAR) asm volatile("bar.sync 15, 256;" ::: "memory");
    }
  }
}

typedef CUresult (*EncodeFn)(CUtensorMap*, CUtensorMapDataType, cuuint32_t, void*, const cuuint64_t*, const cuuint64_t*,
                             const cuuint32_t*, const cuuint32_t*, CUtensorMapInterleave, CUtensorMapSwizzle,
                             CUtensorMapL2promotion, CUtensorMapFloatOOBfill);

void encode(EncodeFn fn, CUtensorMap* tm, const void* base, int rank, const cuuint64_t* dims, const cuuint64_t* strides,
            const cuuint32_t* box, CUtensorMapSwizzle swz) {
  const cuuint32_t ones[3] = {1, 1, 1};
  fn(tm, CU_TENSOR_MAP_DATA_TYPE_BFLOAT16, rank, const_cast<void*>(base), dims, strides, box, ones,
     CU_TENSOR_MAP_INTERLEAVE_NONE, swz, CU_TENSOR_MAP_L2_PROMOTION_L2_128B, CU_TENSOR_MAP_FLOAT_OOB_FILL_NONE);
}

}

extern "C" void kernel_launch(void* const* d_in, const int* in_sizes, int n_in, void* d_out, int out_size) {
  (void)in_sizes; (void)n_in; (void)out_size;
  Params p;
  p.q = (const __nv_bfloat16*)d_in[0];
  p.k = (const __nv_bfloat16*)d_in[1];
  p.v = (const __nv_bfloat16*)d_in[2];
  p.shift_k = (const __nv_bfloat16*)d_in[3];
  p.ssm_k = (const __nv_bfloat16*)d_in[4];
  p.ssm_D = (const __nv_bfloat16*)d_in[5];
  p.wqkv = (const __nv_bfloat16*)d_in[7];
  p.wo = (const __nv_bfloat16*)d_in[8];
  p.gate_w = (const __nv_bfloat16*)d_in[9];
  p.out = (__nv_bfloat16*)d_out;
  p.zero = 0;

  static EncodeFn fn = nullptr;
  static void* yaddr = nullptr;
  if (!fn) {
    cudaDriverEntryPointQueryResult qr;
    void* f = nullptr;
    cudaGetDriverEntryPoint("cuTensorMapEncodeTiled", &f, cudaEnableDefault, &qr);
    fn = (EncodeFn)f;
    cudaGetSymbolAddress(&yaddr, g_Y);
    cudaFuncSetAttribute(fused_kernel, cudaFuncAttributeMaxDynamicSharedMemorySize, SMEM_BYTES);
  }
  Maps m;
  {
    const cuuint64_t dims[3] = {640, 1024, 2}, st[2] = {2560, 1280};
    const cuuint32_t box[3] = {64, 64, 2};
    encode(fn, &m.x, p.q, 3, dims, st, box, CU_TENSOR_MAP_SWIZZLE_128B);
  }
  {
    const cuuint64_t dims[3] = {640, 640, 3}, st[2] = {3840, 1280};
    const cuuint32_t box[3] = {64, 64, 3}, boxt[3] = {16, 64, 3};
    encode(fn, &m.wm, p.wqkv, 3, dims, st, box, CU_TENSOR_MAP_SWIZZLE_128B);
    encode(fn, &m.wt, p.wqkv, 3, dims, st, boxt, CU_TENSOR_MAP_SWIZZLE_32B);
  }
  {
    const cuuint64_t dims[3] = {64, 2048, 10}, st[2] = {1280, 128};
    const cuuint32_t boxk[3] = {64, 35, 1}, boxv[3] = {64, 32, 1};
    encode(fn, &m.k, p.k, 3, dims, st, boxk, CU_TENSOR_MAP_SWIZZLE_128B);
    encode(fn, &m.v, p.v, 3, dims, st, boxv, CU_TENSOR_MAP_SWIZZLE_128B);
  }
  {
    const cuuint64_t dims[3] = {16, 640, 40}, st[2] = {1280, 32};
    const cuuint32_t box[3] = {16, 40, 5};
    encode(fn, &m.wo, p.wo, 3, dims, st, box, CU_TENSOR_MAP_SWIZZLE_32B);
  }
  {
    const cuuint64_t dims[2] = {2048, 640}, st[1] = {Y_PITCH * 16};
    const cuuint32_t box[2] = {64, 80};
    encode(fn, &m.y, yaddr, 2, dims, st, box, CU_TENSOR_MAP_SWIZZLE_128B);
  }
  {
    const cuuint64_t dims[2] = {640, 2048}, st[1] = {1280};
    const cuuint32_t bqm[2] = {64, 128}, bqt[2] = {16, 128}, bom[2] = {64, 16}, bot[2] = {16, 16};
    encode(fn, &m.qm, p.q, 2, dims, st, bqm, CU_TENSOR_MAP_SWIZZLE_128B);
    encode(fn, &m.qt, p.q, 2, dims, st, bqt, CU_TENSOR_MAP_SWIZZLE_32B);
    encode(fn, &m.om, p.out, 2, dims, st, bom, CU_TENSOR_MAP_SWIZZLE_128B);
    encode(fn, &m.ot, p.out, 2, dims, st, bot, CU_TENSOR_MAP_SWIZZLE_32B);
  }
  fused_kernel<<<NCTA, NTHR, SMEM_BYTES>>>(m, p);
}
```

```cpp
#include <cuda.h>
#include <cuda_bf16.h>
#include <cuda_runtime.h>
#include <stdint.h>

namespace {

constexpr int SEQ = 2048, DIM = 640, NCTA = 128, NTHR = 512;

#define TRIG_KB 9
#define KV_KB 2
#define DEV_EXIT 0
#define ATT_GATE 1
#define G_AFTER 0
#define FENCE_LO 0
#define FENCE_HI 0
#define PW1 2
#define PW2 1
#define ENDBAR 0
#define PAD_KB 0
#define Y_ALIAS 1
#define H_EARLY 1
#define WO_LSU 1
#define WP_TRIG (B_KV + 4)
#define NOMB 0
#define SRC_ROT 0
#define WAIT_NS 0
#define WB_TRIG B_USIG
#define G_POS 0
#define TAILF 1
#define T_ISSUE 384
#define T_PF 416
#define T_INIT 448
#define ATT_MERGE 0
#define BMAP 1
#define PRE2 1
#define KV_MIX 0
#define O_DEFER 0
#define TOK_G 1
#define RF_GATE 0
#define WO_TRIG B_WST
#define WL_TRIG B_WOP
#define WO_GATE 1

constexpr uint32_t STAGE_BYTES = 47104, ST_W = 16384, ST_WT = 40960;
constexpr uint32_t O_BYTES = 20480, WO_BYTES = 12800;
constexpr uint32_t OFF_OA = 0;
constexpr uint32_t OFF_QS = 3 * O_BYTES, OFF_QT = OFF_QS + 16384;
constexpr uint32_t OFF_WC = 81920;
constexpr uint32_t OFF_WA = 94720;
constexpr uint32_t OFF_GATE = 145920;
constexpr uint32_t OFF_KVX = 147968;
constexpr uint32_t OFF_D = OFF_GATE + 512;
constexpr uint32_t OFF_CH3 = 163840;
constexpr uint32_t CH_BYTES = 12288, U_BYTES = 4096;
constexpr uint32_t OFF_FT = 225280, OFF_GT = 229376;
constexpr uint32_t OFF_CH0 = 188416;
constexpr uint32_t OFF_KVS = OFF_CH0, KVS_V = 4480, KVS_BYTES = 8576;
constexpr uint32_t OFF_WS = OFF_WA;
constexpr uint32_t OFF_YT = 163840;
constexpr uint32_t OFF_BAR = 231936;
constexpr uint32_t SMEM_BYTES = OFF_BAR + 512;

enum : uint32_t {
  B_FULL1 = 0, B_EMPTY1 = 4, B_S3 = 7, B_FULL2 = 52, B_EMPTY2 = 13, B_U = 8, B_GATE = 12, B_HA = 19, B_HB = 20,
  B_ATTN = 21, B_C34 = 22, B_CONV = 23, B_YFULL = 24, B_EPOCH = 25, B_PREP = 26, B_P1 = 27, B_LAST = 28,
  B_E3 = 29, B_OSIG = 30, B_WOP = 31, B_USIG = 32, B_WST = 33, B_KV = 34, B_KVD = 39, B_HC = 61, B_QF = 62, B_YST = 40,
  B_TOK = 45, B_YSIG = 50
};
constexpr uint32_t OFF_EPOCH = OFF_BAR + 8 * 51;
__device__ __forceinline__ uint32_t off_o(int j) { return j < 4 ? OFF_OA + j * O_BYTES : j < 6 ? OFF_CH0 + (j - 4) * O_BYTES : OFF_OA + (j - 6) * O_BYTES; }
__device__ __forceinline__ uint32_t off_w(int j) { return j < 4 ? OFF_WA + j * WO_BYTES : j == 4 ? OFF_KVX : j == 5 ? OFF_WC : OFF_WA + (j - 6) * WO_BYTES; }
__device__ __forceinline__ int step_src(int hg, int j) { return SRC_ROT ? (hg + j) & 7 : j == 0 ? hg : j <= hg ? j - 1 : j; }
__device__ __forceinline__ bool tail_first(int hg) { return TAILF && (hg & 3) == 3; }
__device__ __forceinline__ uint32_t off_ch(int c) { return (c < 3 ? OFF_CH0 : OFF_CH3 - 3 * CH_BYTES) + c * CH_BYTES; }

#define U_PITCH 264
__device__ __align__(1024) uint4 g_U[DIM * U_PITCH];
__device__ uint4 g_O[NCTA * 1280];
#define g_Y g_U
constexpr int Y_PITCH = U_PITCH;
__device__ uint4 g_WO[64 * 800];
__device__ uint4 g_halo[NCTA * 2 * 7 * 32];
__device__ float g_gate[SEQ + PAD_KB * 256];
__device__ unsigned g_cnt[32 * (1 + 2 * 16 + 8 + NCTA)];
constexpr int C_LAUNCH = 0, C_PREP = 32, C_Y = 32 * 17, C_W = 32 * 33, C_O = 32 * 41;

#define TSM(cond, slot) do { } while (0)
#define TSIF(cond, slot) do { if (__LINE__ >= FENCE_LO && __LINE__ < FENCE_HI) sched_fence(); } while (0)
__device__ __forceinline__ void sched_fence() {
  asm volatile("{\n.reg .pred p;\n.reg .u32 c;\nmov.u32 c, %%clock;\nsetp.eq.u32 p, c, 0;\n@p st.shared.u32 [%0], c;\n}"
               ::"r"(1024 + OFF_EPOCH + 4) : "memory");
}
#define TS(slot) TSIF(true, slot)

struct Params {
  const __nv_bfloat16 *q, *k, *v, *shift_k, *ssm_k, *ssm_D, *wqkv, *wo, *gate_w;
  __nv_bfloat16* out;
  uint32_t zero;
};

#define POLL_NS 0
constexpr int SPIN_LIMIT = 1 << 17;

__device__ __forceinline__ void mbar_init(uint32_t bar, uint32_t count) {
  asm volatile("mbarrier.init.shared::cta.b64 [%0], %1;" ::"r"(bar), "r"(count) : "memory");
}
__device__ __forceinline__ void mbar_expect_tx(uint32_t bar, uint32_t bytes) {
  asm volatile("mbarrier.arrive.expect_tx.shared::cta.b64 _, [%0], %1;" ::"r"(bar), "r"(bytes) : "memory");
}
__device__ __forceinline__ void mbar_arrive(uint32_t bar) {
  asm volatile("mbarrier.arrive.shared::cta.b64 _, [%0];" ::"r"(bar) : "memory");
}
__device__ __forceinline__ void mbar_wait(uint32_t bar, uint32_t parity) {
  uint32_t ok;
  int spins = 0;
  do {
    if (WAIT_NS)
      asm volatile("{\n.reg .pred p;\nmbarrier.try_wait.parity.shared::cta.b64 p, [%1], %2, %3;\nselp.b32 %0, 1, 0, p;\n}"
                   : "=r"(ok) : "r"(bar), "r"(parity), "r"(WAIT_NS) : "memory");
    else
      asm volatile("{\n.reg .pred p;\nmbarrier.try_wait.parity.shared::cta.b64 p, [%1], %2;\nselp.b32 %0, 1, 0, p;\n}"
                   : "=r"(ok) : "r"(bar), "r"(parity) : "memory");
    if (++spins > SPIN_LIMIT) break;
  } while (!ok);
}
__device__ __forceinline__ void flag_poll(const unsigned* p, unsigned target) {
  unsigned v;
  int spins = 0;
  do {
    if (POLL_NS && spins) __nanosleep(POLL_NS);
    asm volatile("ld.relaxed.gpu.global.u32 %0, [%1];" : "=r"(v) : "l"(p) : "memory");
    if (++spins > SPIN_LIMIT) break;
  } while ((int)(v - target) < 0);
}
__device__ __forceinline__ void flag_wait(const unsigned* p, unsigned target) {
  flag_poll(p, target);
  asm volatile("fence.acquire.gpu;\nfence.proxy.async.global;" ::: "memory");
}
__device__ __forceinline__ void flag_signal(unsigned* p, int n, int lane) {
  if (lane == 0) asm volatile("fence.release.gpu;" ::: "memory");
  __syncwarp();
  if (lane < n) asm volatile("red.relaxed.gpu.global.add.u32 [%0], 1;" ::"l"(p + 32 * lane) : "memory");
}
__device__ __forceinline__ void flag_bump(unsigned* p) {
  asm volatile("red.relaxed.gpu.global.add.u32 [%0], 1;" ::"l"(p) : "memory");
}
__device__ __forceinline__ void fence_async_smem() { asm volatile("fence.proxy.async.shared::cta;" ::: "memory"); }
__device__ __forceinline__ void wg_sync(int id) { asm volatile("bar.sync %0, 128;" ::"r"(id) : "memory"); }

__device__ __forceinline__ void tma_2d(uint32_t dst, const CUtensorMap* tm, int c0, int c1, uint32_t bar) {
  asm volatile("cp.async.bulk.tensor.2d.shared::cluster.global.mbarrier::complete_tx::bytes [%0], [%1, {%3, %4}], [%2];"
               ::"r"(dst), "l"(tm), "r"(bar), "r"(c0), "r"(c1) : "memory");
}
__device__ __forceinline__ void tma_3d(uint32_t dst, const CUtensorMap* tm, int c0, int c1, int c2, uint32_t bar) {
  asm volatile("cp.async.bulk.tensor.3d.shared::cluster.global.mbarrier::complete_tx::bytes [%0], [%1, {%3, %4, %5}], [%2];"
               ::"r"(dst), "l"(tm), "r"(bar), "r"(c0), "r"(c1), "r"(c2) : "memory");
}
__device__ __forceinline__ void bulk_load(uint32_t dst, const void* src, uint32_t bytes, uint32_t bar) {
  asm volatile("cp.async.bulk.shared::cluster.global.mbarrier::complete_tx::bytes [%0], [%1], %2, [%3];"
               ::"r"(dst), "l"(src), "r"(bytes), "r"(bar) : "memory");
}
__device__ __forceinline__ void tm_prefetch(const CUtensorMap* tm) {
  asm volatile("prefetch.tensormap [%0];" ::"l"(tm) : "memory");
}

__device__ __forceinline__ void wg_fence() { asm volatile("wgmma.fence.sync.aligned;" ::: "memory"); }
__device__ __forceinline__ void wg_commit() { asm volatile("wgmma.commit_group.sync.aligned;" ::: "memory"); }
template <int N> __device__ __forceinline__ void wg_wait() { asm volatile("wgmma.wait_group.sync.aligned %0;" ::"n"(N) : "memory"); }
__device__ __forceinline__ uint32_t desc_lo(uint32_t addr, uint32_t lbo) { return ((addr & 0x3FFFF) >> 4) | ((lbo >> 4) << 16); }
constexpr uint32_t desc_hi(uint32_t sbo, uint32_t swz) { return (sbo >> 4) | (swz << 30); }
constexpr uint32_t HI_SW128 = desc_hi(1024, 1), HI_SW64 = desc_hi(512, 2), HI_SW32 = desc_hi(256, 3), HI_NONE = desc_hi(128, 0);
template <int N> __device__ __forceinline__ void pin(float* d) {
#pragma unroll
  for (int i = 0; i < N; i++) asm volatile("" : "+f"(d[i])::"memory");
}

__device__ __forceinline__ uint32_t lds32(uint32_t a) {
  uint32_t v;
  asm volatile("ld.volatile.shared.u32 %0, [%1];" : "=r"(v) : "r"(a) : "memory");
  return v;
}
__device__ __forceinline__ uint4 ldg128(const void* a) {
  uint4 v;
  asm volatile("ld.global.nc.v4.u32 {%0, %1, %2, %3}, [%4];" : "=r"(v.x), "=r"(v.y), "=r"(v.z), "=r"(v.w) : "l"(a) : "memory");
  return v;
}
__device__ __forceinline__ uint2 ldg64(const void* a) {
  uint2 v;
  asm volatile("ld.global.nc.v2.u32 {%0, %1}, [%2];" : "=r"(v.x), "=r"(v.y) : "l"(a) : "memory");
  return v;
}
__device__ __forceinline__ void ldsm4(uint32_t* r, uint32_t a) {
  asm volatile("ldmatrix.sync.aligned.m8n8.x4.shared.b16 {%0, %1, %2, %3}, [%4];"
               : "=r"(r[0]), "=r"(r[1]), "=r"(r[2]), "=r"(r[3]) : "r"(a) : "memory");
}
__device__ __forceinline__ void ldsm4t(uint32_t* r, uint32_t a) {
  asm volatile("ldmatrix.sync.aligned.m8n8.x4.trans.shared.b16 {%0, %1, %2, %3}, [%4];"
               : "=r"(r[0]), "=r"(r[1]), "=r"(r[2]), "=r"(r[3]) : "r"(a) : "memory");
}
__device__ __forceinline__ uint4 lds128(uint32_t a) {
  uint4 v;
  asm volatile("ld.shared.v4.u32 {%0, %1, %2, %3}, [%4];" : "=r"(v.x), "=r"(v.y), "=r"(v.z), "=r"(v.w) : "r"(a) : "memory");
  return v;
}
__device__ __forceinline__ void sts128(uint32_t a, uint32_t x, uint32_t y, uint32_t z, uint32_t w) {
  asm volatile("st.shared.v4.u32 [%0], {%1, %2, %3, %4};" ::"r"(a), "r"(x), "r"(y), "r"(z), "r"(w) : "memory");
}
__device__ __forceinline__ void stsm4(uint32_t a, const uint32_t* r) {
  asm volatile("stmatrix.sync.aligned.m8n8.x4.shared.b16 [%0], {%1, %2, %3, %4};" ::"r"(a), "r"(r[0]), "r"(r[1]), "r"(r[2]), "r"(r[3]) : "memory");
}
__device__ __forceinline__ void stsm4t(uint32_t a, const uint32_t* r) {
  asm volatile("stmatrix.sync.aligned.m8n8.x4.trans.shared.b16 [%0], {%1, %2, %3, %4};" ::"r"(a), "r"(r[0]), "r"(r[1]), "r"(r[2]), "r"(r[3]) : "memory");
}
__device__ __forceinline__ uint32_t pack2(float lo, float hi) {
  uint32_t r;
  asm("cvt.rn.bf16x2.f32 %0, %1, %2;" : "=r"(r) : "f"(hi), "f"(lo));
  return r;
}
__device__ __forceinline__ uint32_t movm(uint32_t a) {
  uint32_t d;
  asm volatile("movmatrix.sync.aligned.m8n8.trans.b16 %0, %1;" : "=r"(d) : "r"(a));
  return d;
}
__device__ __forceinline__ uint32_t bmul(uint32_t a, uint32_t b) {
  uint32_t d;
  asm("mul.rn.bf16x2 %0, %1, %2;" : "=r"(d) : "r"(a), "r"(b));
  return d;
}
__device__ __forceinline__ uint32_t badd(uint32_t a, uint32_t b) {
  uint32_t d;
  asm("add.rn.bf16x2 %0, %1, %2;" : "=r"(d) : "r"(a), "r"(b));
  return d;
}
__device__ __forceinline__ float bf_lo(uint32_t x) { return __uint_as_float(x << 16); }
__device__ __forceinline__ float bf_hi(uint32_t x) { return __uint_as_float(x & 0xFFFF0000u); }
__device__ __forceinline__ float ex2(float x) {
  float y;
  asm("ex2.approx.ftz.f32 %0, %1;" : "=f"(y) : "f"(x));
  return y;
}
__device__ __forceinline__ float rcp(float x) {
  float y;
  asm("rcp.approx.ftz.f32 %0, %1;" : "=f"(y) : "f"(x));
  return y;
}
__device__ __forceinline__ void mma16816(float* d, uint32_t a0, uint32_t a1, uint32_t a2, uint32_t a3, uint32_t b0, uint32_t b1) {
  asm volatile("mma.sync.aligned.m16n8k16.row.col.f32.bf16.bf16.f32 {%0, %1, %2, %3}, {%4, %5, %6, %7}, {%8, %9}, {%0, %1, %2, %3};"
               : "+f"(d[0]), "+f"(d[1]), "+f"(d[2]), "+f"(d[3])
               : "r"(a0), "r"(a1), "r"(a2), "r"(a3), "r"(b0), "r"(b1));
}
__device__ __forceinline__ void mma1688(float* d, uint32_t a0, uint32_t a1, uint32_t b0) {
  asm volatile("mma.sync.aligned.m16n8k8.row.col.f32.bf16.bf16.f32 {%0, %1, %2, %3}, {%4, %5}, {%6}, {%0, %1, %2, %3};"
               : "+f"(d[0]), "+f"(d[1]), "+f"(d[2]), "+f"(d[3])
               : "r"(a0), "r"(a1), "r"(b0));
}

template <int N> struct WgRS;
template <int N> struct WgSST;
template <> struct WgRS<32> {
  template <uint32_t HB>
  static __device__ __forceinline__ void mma(float* d, const uint32_t* a, uint32_t db) {
    asm volatile("{\n.reg .pred p;\n.reg .b64 db;\nsetp.ne.b32 p, %22, 0;\n"
      "mov.b64 db, {%20, %21};\n"
      "wgmma.mma_async.sync.aligned.m64n32k16.f32.bf16.bf16 {"
      "%0, %1, %2, %3, %4, %5, %6, %7, %8, %9, %10, %11, %12, %13, %14, %15"
      "}, {%16, %17, %18, %19}, db, p, 1, 1, 1;\n}\n"
      : "+f"(d[0]), "+f"(d[1]), "+f"(d[2]), "+f"(d[3]), "+f"(d[4]), "+f"(d[5]), "+f"(d[6]), "+f"(d[7]),
        "+f"(d[8]), "+f"(d[9]), "+f"(d[10]), "+f"(d[11]), "+f"(d[12]), "+f"(d[13]), "+f"(d[14]), "+f"(d[15])
      : "r"(a[0]), "r"(a[1]), "r"(a[2]), "r"(a[3]), "r"(db), "n"(HB), "n"(1));
  }
  template <uint32_t HB>
  static __device__ __forceinline__ void set(float* d, const uint32_t* a, uint32_t db) {
    asm volatile("{\n.reg .pred p;\n.reg .b64 db;\nsetp.ne.b32 p, %22, 0;\n"
      "mov.b64 db, {%20, %21};\n"
      "wgmma.mma_async.sync.aligned.m64n32k16.f32.bf16.bf16 {"
      "%0, %1, %2, %3, %4, %5, %6, %7, %8, %9, %10, %11, %12, %13, %14, %15"
      "}, {%16, %17, %18, %19}, db, p, 1, 1, 1;\n}\n"
      : "=f"(d[0]), "=f"(d[1]), "=f"(d[2]), "=f"(d[3]), "=f"(d[4]), "=f"(d[5]), "=f"(d[6]), "=f"(d[7]),
        "=f"(d[8]), "=f"(d[9]), "=f"(d[10]), "=f"(d[11]), "=f"(d[12]), "=f"(d[13]), "=f"(d[14]), "=f"(d[15])
      : "r"(a[0]), "r"(a[1]), "r"(a[2]), "r"(a[3]), "r"(db), "n"(HB), "n"(0));
  }
};
template <> struct WgRS<64> {
  template <uint32_t HB>
  static __device__ __forceinline__ void mma(float* d, const uint32_t* a, uint32_t db) {
    asm volatile("{\n.reg .pred p;\n.reg .b64 db;\nsetp.ne.b32 p, %38, 0;\n"
      "mov.b64 db, {%36, %37};\n"
      "wgmma.mma_async.sync.aligned.m64n64k16.f32.bf16.bf16 {"
      "%0, %1, %2, %3, %4, %5, %6, %7, %8, %9, %10, %11, %12, %13, %14, %15, "
      "%16, %17, %18, %19, %20, %21, %22, %23, %24, %25, %26, %27, %28, %29, %30, %31"
      "}, {%32, %33, %34, %35}, db, p, 1, 1, 1;\n}\n"
      : "+f"(d[0]), "+f"(d[1]), "+f"(d[2]), "+f"(d[3]), "+f"(d[4]), "+f"(d[5]), "+f"(d[6]), "+f"(d[7]),
        "+f"(d[8]), "+f"(d[9]), "+f"(d[10]), "+f"(d[11]), "+f"(d[12]), "+f"(d[13]), "+f"(d[14]), "+f"(d[15]),
        "+f"(d[16]), "+f"(d[17]), "+f"(d[18]), "+f"(d[19]), "+f"(d[20]), "+f"(d[21]), "+f"(d[22]), "+f"(d[23]),
        "+f"(d[24]), "+f"(d[25]), "+f"(d[26]), "+f"(d[27]), "+f"(d[28]), "+f"(d[29]), "+f"(d[30]), "+f"(d[31])
      : "r"(a[0]), "r"(a[1]), "r"(a[2]), "r"(a[3]), "r"(db), "n"(HB), "n"(1));
  }
  template <uint32_t HB>
  static __device__ __forceinline__ void set(float* d, const uint32_t* a, uint32_t db) {
    asm volatile("{\n.reg .pred p;\n.reg .b64 db;\nsetp.ne.b32 p, %38, 0;\n"
      "mov.b64 db, {%36, %37};\n"
      "wgmma.mma_async.sync.aligned.m64n64k16.f32.bf16.bf16 {"
      "%0, %1, %2, %3, %4, %5, %6, %7, %8, %9, %10, %11, %12, %13, %14, %15, "
      "%16, %17, %18, %19, %20, %21, %22, %23, %24, %25, %26, %27, %28, %29, %30, %31"
      "}, {%32, %33, %34, %35}, db, p, 1, 1, 1;\n}\n"
      : "=f"(d[0]), "=f"(d[1]), "=f"(d[2]), "=f"(d[3]), "=f"(d[4]), "=f"(d[5]), "=f"(d[6]), "=f"(d[7]),
        "=f"(d[8]), "=f"(d[9]), "=f"(d[10]), "=f"(d[11]), "=f"(d[12]), "=f"(d[13]), "=f"(d[14]), "=f"(d[15]),
        "=f"(d[16]), "=f"(d[17]), "=f"(d[18]), "=f"(d[19]), "=f"(d[20]), "=f"(d[21]), "=f"(d[22]), "=f"(d[23]),
        "=f"(d[24]), "=f"(d[25]), "=f"(d[26]), "=f"(d[27]), "=f"(d[28]), "=f"(d[29]), "=f"(d[30]), "=f"(d[31])
      : "r"(a[0]), "r"(a[1]), "r"(a[2]), "r"(a[3]), "r"(db), "n"(HB), "n"(0));
  }
};
template <> struct WgSST<48> {
  template <uint32_t HA, uint32_t HB>
  static __device__ __forceinline__ void mma(float* d, uint32_t da, uint32_t db, int sc) {
    asm volatile("{\n.reg .pred p;\n.reg .b64 da, db;\nsetp.ne.b32 p, %28, 0;\n"
      "mov.b64 da, {%24, %25};\nmov.b64 db, {%26, %27};\n"
      "wgmma.mma_async.sync.aligned.m64n48k16.f32.bf16.bf16 {"
      "%0, %1, %2, %3, %4, %5, %6, %7, %8, %9, %10, %11, %12, %13, %14, %15, "
      "%16, %17, %18, %19, %20, %21, %22, %23"
      "}, da, db, p, 1, 1, 0, 1;\n}\n"
      : "+f"(d[0]), "+f"(d[1]), "+f"(d[2]), "+f"(d[3]), "+f"(d[4]), "+f"(d[5]), "+f"(d[6]), "+f"(d[7]),
        "+f"(d[8]), "+f"(d[9]), "+f"(d[10]), "+f"(d[11]), "+f"(d[12]), "+f"(d[13]), "+f"(d[14]), "+f"(d[15]),
        "+f"(d[16]), "+f"(d[17]), "+f"(d[18]), "+f"(d[19]), "+f"(d[20]), "+f"(d[21]), "+f"(d[22]), "+f"(d[23])
      : "r"(da), "n"(HA), "r"(db), "n"(HB), "r"(sc));
  }
};
template <> struct WgSST<80> {
  template <uint32_t HA, uint32_t HB>
  static __device__ __forceinline__ void mma(float* d, uint32_t da, uint32_t db, int sc) {
    asm volatile("{\n.reg .pred p;\n.reg .b64 da, db;\nsetp.ne.b32 p, %44, 0;\n"
      "mov.b64 da, {%40, %41};\nmov.b64 db, {%42, %43};\n"
      "wgmma.mma_async.sync.aligned.m64n80k16.f32.bf16.bf16 {"
      "%0, %1, %2, %3, %4, %5, %6, %7, %8, %9, %10, %11, %12, %13, %14, %15, "
      "%16, %17, %18, %19, %20, %21, %22, %23, %24, %25, %26, %27, %28, %29, %30, %31, "
      "%32, %33, %34, %35, %36, %37, %38, %39"
      "}, da, db, p, 1, 1, 0, 1;\n}\n"
      : "+f"(d[0]), "+f"(d[1]), "+f"(d[2]), "+f"(d[3]), "+f"(d[4]), "+f"(d[5]), "+f"(d[6]), "+f"(d[7]),
        "+f"(d[8]), "+f"(d[9]), "+f"(d[10]), "+f"(d[11]), "+f"(d[12]), "+f"(d[13]), "+f"(d[14]), "+f"(d[15]),
        "+f"(d[16]), "+f"(d[17]), "+f"(d[18]), "+f"(d[19]), "+f"(d[20]), "+f"(d[21]), "+f"(d[22]), "+f"(d[23]),
        "+f"(d[24]), "+f"(d[25]), "+f"(d[26]), "+f"(d[27]), "+f"(d[28]), "+f"(d[29]), "+f"(d[30]), "+f"(d[31]),
        "+f"(d[32]), "+f"(d[33]), "+f"(d[34]), "+f"(d[35]), "+f"(d[36]), "+f"(d[37]), "+f"(d[38]), "+f"(d[39])
      : "r"(da), "n"(HA), "r"(db), "n"(HB), "r"(sc));
  }
};
template <> struct WgSST<192> {
  template <uint32_t HA, uint32_t HB>
  static __device__ __forceinline__ void mma(float* d, uint32_t da, uint32_t db, int sc) {
    asm volatile("{\n.reg .pred p;\n.reg .b64 da, db;\nsetp.ne.b32 p, %100, 0;\n"
      "mov.b64 da, {%96, %97};\nmov.b64 db, {%98, %99};\n"
      "wgmma.mma_async.sync.aligned.m64n192k16.f32.bf16.bf16 {"
      "%0, %1, %2, %3, %4, %5, %6, %7, %8, %9, %10, %11, %12, %13, %14, %15, "
      "%16, %17, %18, %19, %20, %21, %22, %23, %24, %25, %26, %27, %28, %29, %30, %31, "
      "%32, %33, %34, %35, %36, %37, %38, %39, %40, %41, %42, %43, %44, %45, %46, %47, "
      "%48, %49, %50, %51, %52, %53, %54, %55, %56, %57, %58, %59, %60, %61, %62, %63, "
      "%64, %65, %66, %67, %68, %69, %70, %71, %72, %73, %74, %75, %76, %77, %78, %79, "
      "%80, %81, %82, %83, %84, %85, %86, %87, %88, %89, %90, %91, %92, %93, %94, %95"
      "}, da, db, p, 1, 1, 0, 1;\n}\n"
      : "+f"(d[0]), "+f"(d[1]), "+f"(d[2]), "+f"(d[3]), "+f"(d[4]), "+f"(d[5]), "+f"(d[6]), "+f"(d[7]),
        "+f"(d[8]), "+f"(d[9]), "+f"(d[10]), "+f"(d[11]), "+f"(d[12]), "+f"(d[13]), "+f"(d[14]), "+f"(d[15]),
        "+f"(d[16]), "+f"(d[17]), "+f"(d[18]), "+f"(d[19]), "+f"(d[20]), "+f"(d[21]), "+f"(d[22]), "+f"(d[23]),
        "+f"(d[24]), "+f"(d[25]), "+f"(d[26]), "+f"(d[27]), "+f"(d[28]), "+f"(d[29]), "+f"(d[30]), "+f"(d[31]),
        "+f"(d[32]), "+f"(d[33]), "+f"(d[34]), "+f"(d[35]), "+f"(d[36]), "+f"(d[37]), "+f"(d[38]), "+f"(d[39]),
        "+f"(d[40]), "+f"(d[41]), "+f"(d[42]), "+f"(d[43]), "+f"(d[44]), "+f"(d[45]), "+f"(d[46]), "+f"(d[47]),
        "+f"(d[48]), "+f"(d[49]), "+f"(d[50]), "+f"(d[51]), "+f"(d[52]), "+f"(d[53]), "+f"(d[54]), "+f"(d[55]),
        "+f"(d[56]), "+f"(d[57]), "+f"(d[58]), "+f"(d[59]), "+f"(d[60]), "+f"(d[61]), "+f"(d[62]), "+f"(d[63]),
        "+f"(d[64]), "+f"(d[65]), "+f"(d[66]), "+f"(d[67]), "+f"(d[68]), "+f"(d[69]), "+f"(d[70]), "+f"(d[71]),
        "+f"(d[72]), "+f"(d[73]), "+f"(d[74]), "+f"(d[75]), "+f"(d[76]), "+f"(d[77]), "+f"(d[78]), "+f"(d[79]),
        "+f"(d[80]), "+f"(d[81]), "+f"(d[82]), "+f"(d[83]), "+f"(d[84]), "+f"(d[85]), "+f"(d[86]), "+f"(d[87]),
        "+f"(d[88]), "+f"(d[89]), "+f"(d[90]), "+f"(d[91]), "+f"(d[92]), "+f"(d[93]), "+f"(d[94]), "+f"(d[95])
      : "r"(da), "n"(HA), "r"(db), "n"(HB), "r"(sc));
  }
};

struct FftConst {
  uint32_t f[2][4], fi[4][4];
  float ta[4], tb[4];
};
__device__ __forceinline__ void cis(int m, float scale, float& c, float& s) {
  const float a = (float)m * (-6.283185307179586f * scale);
  c = __cosf(a);
  s = __sinf(a);
}
__device__ __forceinline__ void fft_tables(uint32_t (&v)[12], int tw) {
  const int row = tw >> 2, ch = tw & 3;
#pragma unroll
  for (int i = 0; i < 4; i++) {
    float c[2], s[2], x[2];
#pragma unroll
    for (int e = 0; e < 2; e++) {
      cis((((32 * (8 * ch + 2 * i + e) + 15) * (4 * row - 63) + 2048) & 4095) - 2048, 1.f / 4096, c[e], s[e]);
      float gc, gs;
      cis((((row & 15) * (8 * (ch & 1) + 2 * i + e) + 8) & 15) - 8, 1.f / 16, gc, gs);
      x[e] = (row >> 4) == (ch >> 1) ? gc : (ch >> 1) ? gs : -gs;
    }
    v[i] = pack2(c[0] * 0.125f, c[1] * 0.125f);
    v[4 + i] = pack2(s[0] * 0.125f, s[1] * 0.125f);
    v[8 + i] = pack2(x[0], x[1]);
  }
#pragma unroll
  for (int i = 0; i < 12; i++) asm volatile("" : "+r"(v[i]));
}
__device__ __forceinline__ void fft_tables_store(const uint32_t (&v)[12], uint32_t sb, int tw) {
  const int row = tw >> 2;
  const uint32_t x = ((tw ^ (row >> 1)) & 3) << 4, a = sb + OFF_FT + (16 * (row >> 3) + (row & 7)) * 64 + x;
  sts128(a, v[0], v[1], v[2], v[3]);
  sts128(a + 512, v[4], v[5], v[6], v[7]);
  sts128(sb + OFF_GT + row * 64 + x, v[8], v[9], v[10], v[11]);
}
__device__ __forceinline__ void fft_twiddles(FftConst& k, int w, int lane) {
#pragma unroll
  for (int i = 0; i < 4; i++) {
    float c, s;
    cis((2 * (8 * (i >> 1) + 2 * (lane & 3) + (i & 1)) - 15) * (4 * (8 * w + (lane >> 2)) - 63), 1.f / 4096, c, s);
    k.ta[i] = __fdividef(-s, 1.f + c);
    k.tb[i] = s;
  }
  pin<4>(k.ta);
  pin<4>(k.tb);
}
__device__ __forceinline__ void fft_matrices(FftConst& k, uint32_t sb, int w, int lane) {
  const uint32_t x = (lane >> 1) & 3;
#pragma unroll
  for (int i = 0; i < 2; i++) {
    ldsm4(k.f[i], sb + OFF_FT + (16 * w + (lane & 15)) * 64 + (((2 * i + (lane >> 4)) ^ x) << 4));
    ldsm4t(k.fi[i], sb + OFF_FT + (32 * i + lane) * 64 + ((w ^ x) << 4));
#pragma unroll
    for (int j = 0; j < 4; j++) {
      k.fi[2 + i][j] = (j & 1) ? k.fi[i][j - 1] ^ 0x80008000u : k.fi[i][j + 1];
      asm volatile("" : "+r"(k.fi[2 + i][j]));
    }
  }
}
template <bool INV> __device__ __forceinline__ void rot(float& x, float& y, float a, float b) {
  x = fmaf(INV ? -a : a, y, x);
  y = fmaf(INV ? -b : b, x, y);
  x = fmaf(INV ? -a : a, y, x);
}
__device__ __forceinline__ void twiddle_fwd(uint32_t (&a)[4][4], float* d, const FftConst& k) {
#pragma unroll
  for (int q = 0; q < 4; q++)
#pragma unroll
    for (int j = 0; j < 2; j++) {
      float* x = d + 8 * q + 4 * j;
      rot<false>(x[0], x[2], k.ta[2 * j], k.tb[2 * j]);
      rot<false>(x[1], x[3], k.ta[2 * j + 1], k.tb[2 * j + 1]);
      a[q & 2][2 * j + (q & 1)] = pack2(x[0], x[1]);
      a[(q & 2) + 1][2 * j + (q & 1)] = pack2(x[2], x[3]);
    }
}
__device__ __forceinline__ void g_step(float* d, const uint32_t (&a)[4][4], uint32_t dre, uint32_t dim) {
  WgRS<32>::set<HI_SW64>(d, a[0], dre);
  WgRS<32>::set<HI_SW64>(d + 16, a[2], dre);
  WgRS<32>::mma<HI_SW64>(d, a[1], dim);
  WgRS<32>::mma<HI_SW64>(d + 16, a[3], dim);
  wg_commit();
}

__device__ __forceinline__ void conv_channel(const FftConst& k, uint32_t sb, int c, int wg, int w, int lane) {
  const uint32_t cb = sb + off_ch(c), bars = sb + OFF_BAR;
  const uint32_t du = desc_lo(cb, 1024), dg = desc_lo(sb + OFF_GT, 16), dz = desc_lo(cb + U_BYTES, 16);
  float U[32], H[32];
  uint32_t a[4][4], e[4][4];
  const float dv = __uint_as_float(lds32(sb + OFF_D + 4 * c));
  wg_fence();
  WgRS<64>::set<HI_SW32>(H, k.f[0], du + 256);
  WgRS<64>::mma<HI_SW32>(H, k.f[1], du + 256 + 32);
  wg_commit();
  wg_wait<0>();
  pin<32>(H);
  twiddle_fwd(a, H, k);
  if (ATT_GATE && H_EARLY) mbar_wait(bars + 8 * B_ATTN, 0);
  mbar_wait(bars + 8 * (B_U + (c < 3 ? c : 3)), 0);
  TSM(w == 0 && c < 3, 7 + wg);
  if (TOK_G < 8 && c > 0) mbar_wait(bars + 8 * (B_TOK + c - 1), 0);
  wg_fence();
  WgRS<64>::set<HI_SW32>(U, k.f[0], du);
  WgRS<64>::mma<HI_SW32>(U, k.f[1], du + 32);
  wg_commit();
  g_step(H, a, dg, dg + 64);
  wg_wait<1>();
  pin<32>(U);
  if (TOK_G == 1 && lane == 0) mbar_arrive(bars + 8 * (B_TOK + c));
  twiddle_fwd(e, U, k);
  wg_fence();
  g_step(U, e, dg, dg + 64);
  if (TOK_G == 2 && lane == 0) mbar_arrive(bars + 8 * (B_TOK + c));
  wg_wait<0>();
  pin<32>(U);
  pin<32>(H);
#pragma unroll
  for (int j = 0; j < 2; j++) {
    float pr[4][2], pi[4][2];
#pragma unroll
    for (int x = 0; x < 2; x++) {
      H[4 * j + x] += dv;
#pragma unroll
      for (int m = 0; m < 4; m++) {
#pragma unroll
        for (int q = 0; q <= m; q++) {
          const int ih = 16 * (q >> 1) + 2 * (q & 1) + 4 * j + x, iu = 16 * ((m - q) >> 1) + 2 * ((m - q) & 1) + 4 * j + x;
          pr[m][x] = q ? fmaf(H[ih], U[iu], pr[m][x]) : H[ih] * U[iu];
          pi[m][x] = q ? fmaf(H[ih], U[iu + 8], pi[m][x]) : H[ih] * U[iu + 8];
          pr[m][x] = fmaf(-H[ih + 8], U[iu + 8], pr[m][x]);
          pi[m][x] = fmaf(H[ih + 8], U[iu], pi[m][x]);
        }
      }
    }
#pragma unroll
    for (int m = 0; m < 4; m++) {
      a[m & 2][2 * j + (m & 1)] = pack2(pr[m][0], pr[m][1]);
      a[(m & 2) + 1][2 * j + (m & 1)] = pack2(pi[m][0], pi[m][1]);
    }
  }
  wg_fence();
  g_step(U, a, dg + 64, dg);
  if (TOK_G == 3 && lane == 0) mbar_arrive(bars + 8 * (B_TOK + c));
  const uint32_t za = cb + U_BYTES + (8 * w + (lane & 7)) * 128 + (((lane >> 3) ^ (lane & 7)) << 4);
  const uint32_t ya = cb + (lane >> 4) * 1024 + (8 * w + (lane & 7)) * 32 + ((((lane >> 3) ^ (lane >> 2)) & 1) << 4);
  wg_sync(1 + wg);
  wg_wait<0>();
  pin<32>(U);
  TSIF(w == 0, 80 + c);
#pragma unroll
  for (int p = 0; p < 2; p++) {
#pragma unroll
    for (int i = 0; i < 4; i++) {
      const int j = i & 1;
      float* x = U + 16 * p + 4 * j + (i & 2);
      rot<true>(x[8], x[0], k.ta[2 * j], k.tb[2 * j]);
      rot<true>(x[9], x[1], k.ta[2 * j + 1], k.tb[2 * j + 1]);
      e[p][i] = pack2(x[8], x[9]);
      e[2 + p][i] = pack2(x[0], x[1]);
    }
    stsm4(za ^ (64 * p), e[p]);
    stsm4((za ^ (64 * p)) + 4096, e[2 + p]);
  }
  fence_async_smem();
  wg_sync(1 + wg);
  wg_fence();
  WgRS<64>::set<HI_SW128>(H, k.fi[0], dz);
#pragma unroll
  for (int ks = 1; ks < 4; ks++) WgRS<64>::mma<HI_SW128>(H, k.fi[ks], dz + 128 * ks);
  wg_commit();
  wg_wait<0>();
  pin<32>(H);
  TSIF(w == 0, 88 + c);
#pragma unroll
  for (int j = 0; j < 8; j++)
    a[j >> 2][j & 3] = j < 2 ? pack2(H[4 * j], H[4 * j + 1]) : pack2(H[4 * j] + H[4 * j - 6], H[4 * j + 1] + H[4 * j - 5]);
  stsm4(ya, a[0]);
  stsm4(ya + 2048, a[1]);
  fence_async_smem();
  __syncwarp();
}

__device__ __forceinline__ void prep_slab(uint4* res, const uint2* sw, uint32_t sb, int slab, int w, int lane) {
  const int t = lane & 3, tp = (lane & 7) >> 1, pos = 8 * tp + 2 * (((lane >> 3) + tp) & 3) + (lane & 1);
  const uint32_t base = sb + OFF_KVS + slab * KVS_BYTES + pos * 128;
  uint32_t kk[2][4][4], vv[2][4];
  mbar_wait(sb + OFF_BAR + 8 * (B_KV + slab), 0);
#pragma unroll
  for (int h = 0; h < 2; h++) {
#pragma unroll
    for (int j = 0; j < 4; j++) {
      const uint32_t a = base + 128 * j;
      ldsm4t(kk[h][j], a + (((w + 4 * h) ^ ((a >> 7) & 7)) << 4));
    }
    const uint32_t a = base + KVS_V;
    ldsm4t(vv[h], a + (((w + 4 * h) ^ ((a >> 7) & 7)) << 4));
  }
#pragma unroll
  for (int h = 0; h < 2; h++) {
    uint32_t (&k)[4][4] = kk[h];
    uint32_t (&v)[4] = vv[h];
    const uint32_t w0 = __byte_perm(sw[h].x, 0, 0x1010), w1 = __byte_perm(sw[h].x, 0, 0x3232);
    const uint32_t w2 = __byte_perm(sw[h].y, 0, 0x1010), w3 = __byte_perm(sw[h].y, 0, 0x3232);
#pragma unroll
    for (int m = 0; m < 4; m++)
      v[m] = bmul(badd(badd(badd(bmul(k[0][m], w3), bmul(k[1][m], w2)), bmul(k[2][m], w1)), bmul(k[3][m], w0)), v[m]);
    uint32_t a[4];
#pragma unroll
    for (int m = 0; m < 4; m++) a[m] = (t & 1) ? v[(m + 3) & 3] : v[m];
    res[h] = (t & 2) ? make_uint4(a[2], a[3], a[0], a[1]) : make_uint4(a[0], a[1], a[2], a[3]);
  }
}

__device__ __forceinline__ void prep_gate(const Params& p, int b, int w, int lane) {
  uint2 gw[5], x[4][5];
#pragma unroll
  for (int j = 0; j < 5; j++) gw[j] = ldg64(reinterpret_cast<const uint2*>(p.gate_w) + lane + 32 * j);
#pragma unroll
  for (int i = 0; i < 4; i++)
#pragma unroll
    for (int j = 0; j < 5; j++)
      x[i][j] = ldg64(reinterpret_cast<const uint2*>(p.q) + (16 * b + 4 * w + i) * (DIM / 4) + lane + 32 * j);
  float s[4];
#pragma unroll
  for (int i = 0; i < 4; i++) {
    s[i] = 0.f;
#pragma unroll
    for (int j = 0; j < 5; j++) {
      const uint32_t m0 = bmul(x[i][j].x, gw[j].x), m1 = bmul(x[i][j].y, gw[j].y);
      s[i] += (bf_lo(m0) + bf_hi(m0)) + (bf_lo(m1) + bf_hi(m1));
    }
  }
  const bool h = lane & 16, q = lane & 8;
  const float a = (h ? s[2] : s[0]) + __shfl_xor_sync(0xffffffffu, h ? s[0] : s[2], 16);
  const float c = (h ? s[3] : s[1]) + __shfl_xor_sync(0xffffffffu, h ? s[1] : s[3], 16);
  float z = (q ? c : a) + __shfl_xor_sync(0xffffffffu, q ? a : c, 8);
#pragma unroll
  for (int o = 4; o > 0; o >>= 1) z += __shfl_xor_sync(0xffffffffu, z, o);
  z = bf_lo(pack2(z, 0.f));
  if ((lane & 7) == 0) g_gate[16 * b + 4 * w + (lane >> 3)] = bf_lo(pack2(__fdividef(1.f, 1.f + __expf(-z)), 0.f));
}

__device__ __forceinline__ uint32_t bmax(uint32_t a, uint32_t b) {
  uint32_t d;
  asm("max.bf16x2 %0, %1, %2;" : "=r"(d) : "r"(a), "r"(b));
  return d;
}
__device__ __forceinline__ void softmax_two(const float (&l)[2][2], uint32_t& p0, uint32_t& p1) {
  constexpr float kScale = 0.22360679774997896f, kLog2e = 1.4426950408889634f;
  const uint32_t r0 = pack2(l[0][0], l[1][0]), r1 = pack2(l[0][1], l[1][1]);
  const uint32_t x0 = pack2(bf_lo(r0) * kScale, bf_hi(r0) * kScale), x1 = pack2(bf_lo(r1) * kScale, bf_hi(r1) * kScale);
  uint32_t m = bmax(x0, x1);
  m = bmax(m, __shfl_xor_sync(0xffffffffu, m, 1));
  m = bmax(m, __shfl_xor_sync(0xffffffffu, m, 2));
  const float m0 = bf_lo(m) * kLog2e, m1 = bf_hi(m) * kLog2e;
  p0 = pack2(ex2(bf_lo(x0) * kLog2e - m0), ex2(bf_lo(x1) * kLog2e - m0));
  p1 = pack2(ex2(bf_hi(x0) * kLog2e - m1), ex2(bf_hi(x1) * kLog2e - m1));
}

__device__ __forceinline__ void halo_read(uint32_t (&kpv)[10], uint32_t (&vpv)[10], uint32_t (&tg)[7], const uint4* hp) {
#pragma unroll
  for (int j = 0; j < 7; j++) {
    uint32_t x0, x1, x2;
    asm volatile("ld.relaxed.gpu.global.v4.u32 {%0, %1, %2, %3}, [%4];"
                 : "=r"(x0), "=r"(x1), "=r"(x2), "=r"(tg[j]) : "l"(hp + 32 * j) : "memory");
    if (j < 4) kpv[3 * j] = x0; else vpv[3 * j - 10] = x0;
    if (j < 3) kpv[3 * j + 1] = x1; else vpv[3 * j - 9] = x1;
    if (j < 3) kpv[3 * j + 2] = x2; else if (j < 6) vpv[3 * j - 8] = x2;
  }
}

template <int ROT>
__device__ __forceinline__ void pack_qkv(const float* acc, uint32_t (&qlo)[10], uint32_t (&qhi)[10], uint32_t (&klo)[10],
                                         uint32_t (&khi)[10], uint32_t (&vlo)[10], uint32_t (&vhi)[10]) {
#pragma unroll
  for (int j = 0; j < 10; j++) {
    const int x = (j + ROT) % 10, tq = x < 8 ? x : 16 + x, tk = x < 8 ? 8 + x : 18 + x, tv = x < 8 ? 16 + x : 20 + x;
    khi[j] = pack2(acc[4 * tk + 2], acc[4 * tk + 3]);
    vhi[j] = movm(pack2(acc[4 * tv + 2], acc[4 * tv + 3]));
    qlo[j] = pack2(acc[4 * tq], acc[4 * tq + 1]);
    qhi[j] = pack2(acc[4 * tq + 2], acc[4 * tq + 3]);
    klo[j] = pack2(acc[4 * tk], acc[4 * tk + 1]);
    vlo[j] = pack2(acc[4 * tv], acc[4 * tv + 1]);
    asm volatile("" : "+r"(khi[j]), "+r"(qlo[j]), "+r"(qhi[j]), "+r"(klo[j]), "+r"(vlo[j]));
  }
}

__device__ __forceinline__ void attention(float* acc, uint32_t sb, int b, int par, int w, int lane) {
  const int g = lane >> 2, t = lane & 3;
  uint32_t klo[10], khi[10], vlo[10], vhi[10], qlo[10], qhi[10], kpv[10], vpv[10];
  if (tail_first(b & 7)) pack_qkv<8>(acc, qlo, qhi, klo, khi, vlo, vhi);
  else pack_qkv<0>(acc, qlo, qhi, klo, khi, vlo, vhi);
  uint32_t tag = 0;
  if (w == 0 || w == 3) {
    mbar_wait(sb + OFF_BAR + 8 * B_EPOCH, 0);
    tag = lds32(sb + OFF_EPOCH) + 1;
  }
  const uint32_t xa = sb + OFF_KVX + (par * 3) * 2560 + lane * 16;
  if (w < 3) {
    mbar_wait(sb + OFF_BAR + 8 * B_S3, 0);
    sts128(xa + w * 2560, khi[0], khi[1], khi[2], khi[3]);
    sts128(xa + w * 2560 + 512, khi[4], khi[5], khi[6], khi[7]);
    sts128(xa + w * 2560 + 1024, khi[8], khi[9], vhi[0], vhi[1]);
    sts128(xa + w * 2560 + 1536, vhi[2], vhi[3], vhi[4], vhi[5]);
    sts128(xa + w * 2560 + 2048, vhi[6], vhi[7], vhi[8], vhi[9]);
  } else if (b < NCTA - 8) {
    uint4* ho = g_halo + (b * 2 + par) * 224 + lane;
#pragma unroll
    for (int j = 0; j < 7; j++) {
      const uint32_t x0 = j < 4 ? khi[3 * j] : vhi[3 * j - 10], x1 = j < 3 ? khi[3 * j + 1] : vhi[3 * j - 9];
      const uint32_t x2 = j < 3 ? khi[3 * j + 2] : j < 6 ? vhi[3 * j - 8] : 0u;
      asm volatile("st.relaxed.gpu.global.v4.u32 [%0], {%1, %2, %3, %4};" ::"l"(ho + 32 * j), "r"(x0), "r"(x1), "r"(x2), "r"(tag) : "memory");
    }
  }
  TSIF(par == 0 && w == 1, 64);
  TSIF(par == 0 && w == 3, 76);
#pragma unroll
  for (int j = 0; j < 10; j++) vlo[j] = movm(vlo[j]);
  const bool far0 = 2 * t > g, far1 = 2 * t + 1 > g;
  const uint32_t mfar = (far0 ? 0x0000FFFFu : 0u) | (far1 ? 0xFFFF0000u : 0u);
  float slo[4][2], shi[4][2], lg[2][2];
  uint32_t phi[4], plo[4], qml[4], qmh[4];
#pragma unroll
  for (int h = 0; h < 4; h++) {
    const int f = h == 0 ? 0 : h == 1 ? 3 : h == 2 ? 5 : 8, hf = h < 2 ? 2 : 7;
    const bool mine = (h & 1) ? t >= 2 : t < 2;
    qml[h] = mine ? qlo[hf] : 0u;
    qmh[h] = mine ? qhi[hf] : 0u;
    float a[4] = {0.f, 0.f, 0.f, 0.f}, c[4] = {0.f, 0.f, 0.f, 0.f};
    mma16816(a, qlo[f], qhi[f], qlo[f + 1], qhi[f + 1], klo[f], klo[f + 1]);
    mma16816(c, qlo[f], qhi[f], qlo[f + 1], qhi[f + 1], khi[f], khi[f + 1]);
    mma1688(a, qml[h], qmh[h], klo[hf]);
    mma1688(c, qml[h], qmh[h], khi[hf]);
    slo[h][0] = a[0];
    slo[h][1] = a[1];
    shi[h][0] = lg[h & 1][0] = far0 ? a[2] : c[2];
    shi[h][1] = lg[h & 1][1] = far1 ? a[3] : c[3];
    if (!ATT_MERGE && (h & 1)) softmax_two(lg, phi[h - 1], phi[h]);
  }
  TSIF(par == 0 && w == 1, 65);
  wg_sync(1 + par);
  TSIF(par == 0 && w == 1, 66);
  const bool nohist = (w == 0) && (b < 8);
  const uint4* hp = g_halo + ((b - 8) * 2 + par) * 224 + lane;
  uint32_t tg[7];
  if (w > 0) {
    const uint4 v0 = lds128(xa + (w - 1) * 2560), v1 = lds128(xa + (w - 1) * 2560 + 512), v2 = lds128(xa + (w - 1) * 2560 + 1024);
    const uint4 v3 = lds128(xa + (w - 1) * 2560 + 1536), v4 = lds128(xa + (w - 1) * 2560 + 2048);
    kpv[0] = v0.x; kpv[1] = v0.y; kpv[2] = v0.z; kpv[3] = v0.w; kpv[4] = v1.x; kpv[5] = v1.y; kpv[6] = v1.z; kpv[7] = v1.w;
    kpv[8] = v2.x; kpv[9] = v2.y; vpv[0] = v2.z; vpv[1] = v2.w; vpv[2] = v3.x; vpv[3] = v3.y; vpv[4] = v3.z; vpv[5] = v3.w;
    vpv[6] = v4.x; vpv[7] = v4.y; vpv[8] = v4.z; vpv[9] = v4.w;
  } else if (nohist) {
#pragma unroll
    for (int j = 0; j < 10; j++) kpv[j] = vpv[j] = 0u;
  } else {
    TSIF(par == 0, 77);
    halo_read(kpv, vpv, tg, hp);
  }
  if (w == 0 && !nohist) {
    int spins = 0;
    while (true) {
      bool ok = true;
#pragma unroll
      for (int j = 0; j < 7; j++) ok = ok && tg[j] == tag;
      if (__all_sync(0xffffffffu, ok) || ++spins > SPIN_LIMIT) break;
      halo_read(kpv, vpv, tg, hp);
    }
    TSIF(par == 0, 79);
  }
#pragma unroll
  for (int h = 0; h < 4; h++) {
    const int f = h == 0 ? 0 : h == 1 ? 3 : h == 2 ? 5 : 8, hf = h < 2 ? 2 : 7;
    float a[4] = {0.f, 0.f, 0.f, 0.f};
    mma16816(a, qlo[f], qhi[f], qlo[f + 1], qhi[f + 1], kpv[f], kpv[f + 1]);
    mma1688(a, qml[h], qmh[h], kpv[hf]);
    const float ninf = __int_as_float(0xff800000);
    lg[h & 1][0] = far0 ? (nohist ? ninf : a[0]) : slo[h][0];
    lg[h & 1][1] = far1 ? (nohist ? ninf : a[1]) : slo[h][1];
    if (h & 1) {
      softmax_two(lg, plo[h - 1], plo[h]);
      if (ATT_MERGE) {
        const float lh[2][2] = {{shi[h - 1][0], shi[h - 1][1]}, {shi[h][0], shi[h][1]}};
        softmax_two(lh, phi[h - 1], phi[h]);
      }
    }
  }
  TSIF(par == 0 && w <= 1, 67 + w);
  uint32_t ov[20];
#pragma unroll
  for (int hp = 0; hp < 2; hp++) {
    const int hf = hp ? 7 : 2;
    float sh[4] = {0.f, 0.f, 0.f, 0.f}, i0 = 0.f, i1 = 0.f;
#pragma unroll
    for (int e = 0; e < 2; e++) {
      const int h = 2 * hp + e, f = h == 0 ? 0 : h == 1 ? 3 : h == 2 ? 5 : 8;
      const uint32_t a0 = plo[h] & mfar, a2 = plo[h] & ~mfar, a3 = phi[h] & mfar, c1 = phi[h] & ~mfar;
      float sum[4] = {0.f, 0.f, 0.f, 0.f};
      mma1688(sum, plo[h], phi[h], 0x3F803F80u);
      const float r0 = rcp(sum[0]), r1 = rcp(sum[2]);
#pragma unroll
      for (int j = f; j < f + 2; j++) {
        float o[4] = {0.f, 0.f, 0.f, 0.f};
        mma16816(o, a0, 0u, a2, a3, vpv[j], vlo[j]);
        mma1688(o, 0u, c1, vhi[j]);
        ov[2 * j] = pack2(o[0] * r0, o[1] * r0);
        ov[2 * j + 1] = pack2(o[2] * r1, o[3] * r1);
      }
      const bool mine = e ? g >= 4 : g < 4;
      mma16816(sh, a0, 0u, a2, a3, mine ? vpv[hf] : 0u, mine ? vlo[hf] : 0u);
      mma1688(sh, 0u, c1, mine ? vhi[hf] : 0u);
      if (e == 0 || t >= 2) {
        i0 = r0;
        i1 = r1;
      }
    }
    ov[2 * hf] = pack2(sh[0] * i0, sh[1] * i0);
    ov[2 * hf + 1] = pack2(sh[2] * i1, sh[3] * i1);
  }
  TS(32 + 4 * par + w);
  mbar_wait(sb + OFF_BAR + 8 * B_P1, 0);
  const uint32_t oa = sb + OFF_OA + (lane >> 4) * 2048 + (32 * w + 2 * (lane & 15) + par) * 16;
#pragma unroll
  for (int j = 0; j < 5; j++) stsm4(oa + 4096 * j, ov + 4 * j);
  TSIF(par == 0 && w == 0, 120);
  fence_async_smem();
  TSIF(par == 0 && w == 0, 121);
  __syncwarp();
  if (lane == 0) mbar_arrive(sb + OFF_BAR + 8 * B_ATTN);
  TSIF(par == 0 && w == 0, 122);
}

struct Maps {
  CUtensorMap x, wm, wt, k, v, y, wo, qm, qt, om, ot;
};

__device__ __forceinline__ void load_stage(uint32_t sb, int kb, int b, const Maps& m) {
  const uint32_t st = sb + (kb & 3) * STAGE_BYTES, bar = sb + OFF_BAR + 8 * (B_FULL1 + (kb & 3));
  const int r = b >> 3, hg = b & 7, slab = kb - KV_KB;
  const bool kv = slab >= 0 && slab < 5;
  const uint32_t kbar = sb + OFF_BAR + 8 * (B_KV + slab), dst = sb + OFF_KVS + slab * KVS_BYTES;
  mbar_expect_tx(bar, STAGE_BYTES);
  if (kv) mbar_expect_tx(kbar, KVS_BYTES);
  tma_3d(st, &m.x, 64 * kb, 64 * r, 0, bar);
  if (kv && KV_MIX) tma_3d(dst, &m.k, 0, 32 * (b >> 1) - 3, 2 * slab + (b & 1), kbar);
  tma_3d(st + ST_W, &m.wm, 80 * hg + (tail_first(hg) ? 16 : 0), 64 * kb, 0, bar);
  if (kv && KV_MIX) tma_3d(dst + KVS_V, &m.v, 0, 32 * (b >> 1), 2 * slab + (b & 1), kbar);
  tma_3d(st + ST_WT, &m.wt, 80 * hg + (tail_first(hg) ? 0 : 64), 64 * kb, 0, bar);
  if (kv && !KV_MIX) tma_3d(dst, &m.k, 0, 32 * (b >> 1) - 3, 2 * slab + (b & 1), kbar);
  if (kv && !KV_MIX) tma_3d(dst + KVS_V, &m.v, 0, 32 * (b >> 1), 2 * slab + (b & 1), kbar);
}

__global__ void __launch_bounds__(NTHR, 1) fused_kernel(const __grid_constant__ Maps m, const Params p) {
  extern __shared__ __align__(1024) uint8_t smem[];
  const uint32_t sb = (uint32_t)__cvta_generic_to_shared(smem);
  const uint32_t bars = sb + OFF_BAR;
  const int tid = threadIdx.x, lane = tid & 31;
  int b = blockIdx.x;
  if (BMAP == 1) b = (((b & 63) >> 3) * 2 + (b & 1)) * 8 + (((b < 64 ? 0x6521 : 0x7430) >> (4 * ((b >> 1) & 3))) & 7);
  if (BMAP == 2) b = ((b & 63) >> 2) * 8 + (((b < 64 ? 0x6521 : 0x7430) >> (4 * (b & 3))) & 7);
  if (BMAP == 3) b = (((b & 63) >> 3) * 2 + (b & 1)) * 8 + (((b < 64 ? 0x7430 : 0x6521) >> (4 * ((b >> 1) & 3))) & 7);
  if (BMAP == 4) b = (((b >> 4) * 2 + (b & 1)) * 8) + ((b >> 1) & 7);
  if (BMAP == 5) b = 127 - b;
  const int r = b >> 3, hg = b & 7;

  if (tid == T_ISSUE) {
    TSM(true, 0);
#pragma unroll
    for (int i = 0; i < 4; i++) mbar_init(bars + 8 * (B_FULL1 + i), 1);
#pragma unroll
    for (int i = 0; i < 3; i++) mbar_init(bars + 8 * (B_KV + i), 1);
    fence_async_smem();
#pragma unroll 1
    for (int kb = 0; kb <= PRE2; kb++) load_stage(sb, kb, b, m);
  } else if (tid >= T_PF && tid < T_PF + 11) {
    tm_prefetch(&m.x + (tid - T_PF));
  } else if (tid == T_INIT) {
#pragma unroll
    for (int i = 0; i < 4; i++) mbar_init(bars + 8 * (B_EMPTY1 + i), 8);
#pragma unroll
    for (int i = 0; i < 8; i++) mbar_init(bars + 8 * (B_FULL2 + i), 1);
#pragma unroll
    for (int i = 0; i < 4; i++) mbar_init(bars + 8 * (B_EMPTY2 + i), 8);
#pragma unroll
    for (int i = 0; i < 4; i++) mbar_init(bars + 8 * (B_U + i), 1);
    mbar_init(bars + 8 * B_HA, 4);
    mbar_init(bars + 8 * B_GATE, 4);
    mbar_init(bars + 8 * B_HB, 1);
    mbar_init(bars + 8 * B_KVD, 4);
    mbar_init(bars + 8 * B_QF, 1);
    mbar_init(bars + 8 * B_ATTN, 8);
    mbar_init(bars + 8 * B_P1, 8);
    mbar_init(bars + 8 * B_C34, 1);
#pragma unroll
    for (int i = 0; i < 5; i++) mbar_init(bars + 8 * (B_YST + i), 4);
#pragma unroll
    for (int i = 0; i < 5; i++) mbar_init(bars + 8 * (B_TOK + i), 4);
    mbar_init(bars + 8 * B_YSIG, 1);
    mbar_init(bars + 8 * B_YFULL, 1);
    mbar_init(bars + 8 * B_EPOCH, 1);
    mbar_init(bars + 8 * B_PREP, 4);
    mbar_init(bars + 8 * B_USIG, 1);
    mbar_init(bars + 8 * B_WST, 1);
#pragma unroll
    for (int i = 3; i < 5; i++) mbar_init(bars + 8 * (B_KV + i), 1);
    mbar_init(bars + 8 * B_E3, 8);
    mbar_init(bars + 8 * B_LAST, 1);
    mbar_init(bars + 8 * B_OSIG, 1);
    mbar_init(bars + 8 * B_WOP, 1);
    fence_async_smem();
  }
  const int warp = __shfl_sync(0xffffffffu, tid >> 5, 0), wg = warp >> 2, w = warp & 3;
  __syncthreads();

  if (wg == 3) {
    asm volatile("setmaxnreg.dec.sync.aligned.u32 56;");
    if (w == 0) {
      if (lane == 0) {
#pragma unroll 1
        for (int kb = 1 + PRE2; kb < 10; kb++) {
          if (kb >= 4) mbar_wait(bars + 8 * (kb == 7 ? B_E3 : B_EMPTY1 + (kb & 3)), (kb >> 3) & 1);
          TSIF(kb >= 4, 44 + kb);
          load_stage(sb, kb, b, m);
          if (kb == TRIG_KB) mbar_arrive(bars + 8 * B_LAST);
        }
        mbar_wait(bars + 8 * B_WOP, 0);
        mbar_wait(bars + 8 * B_P1, 0);
        mbar_wait(bars + 8 * WL_TRIG, 0);
        mbar_wait(bars + 8 * B_EPOCH, 0);
        flag_wait(g_cnt + C_W + 32 * hg, (lds32(sb + OFF_EPOCH) + 1) * 16);
        TS(30);
#pragma unroll 1
        for (int j = 0; j < 8; j++) {
          if (j >= 6) mbar_wait(bars + 8 * (B_EMPTY2 + j - 6), 0);
          if (j == 4) mbar_wait(bars + 8 * B_ATTN, 0);
          TSIF(j >= 6, 100 + j);
          if (RF_GATE && j == 6) mbar_wait(bars + 8 * B_YSIG, 0);
          mbar_expect_tx(bars + 8 * (B_FULL2 + j), j == 0 ? WO_BYTES : j == 5 ? O_BYTES + WO_BYTES + 512 : O_BYTES + WO_BYTES);
          bulk_load(sb + off_w(j), g_WO + (hg * 8 + step_src(hg, j)) * 800, WO_BYTES, bars + 8 * (B_FULL2 + j));
        }
        mbar_wait(bars + 8 * (B_EMPTY2 + 3), 0);
        mbar_expect_tx(bars + 8 * B_QF, O_BYTES);
        tma_2d(sb + OFF_QS, &m.qm, 80 * hg, 128 * r, bars + 8 * B_QF);
        tma_2d(sb + OFF_QT, &m.qt, 80 * hg + 64, 128 * r, bars + 8 * B_QF);
      }
    } else if (w == 1) {
      unsigned epoch = 0;
      if (lane == 0) {
        epoch = atomicAdd(g_cnt + C_LAUNCH, 1u) / NCTA;
        asm volatile("st.shared.u32 [%0], %1;" ::"r"(sb + OFF_EPOCH), "r"(epoch) : "memory");
        mbar_arrive(bars + 8 * B_EPOCH);
        mbar_wait(bars + 8 * B_KVD, 0);
        mbar_expect_tx(bars + 8 * B_HB, 5 * 4096);
#pragma unroll 1
        for (int c = 0; c < 5; c++) {
          if (c == 3) mbar_wait(bars + 8 * B_S3, 0);
          bulk_load(sb + off_ch(c) + U_BYTES, p.ssm_k + (5 * b + c) * SEQ, 4096, bars + 8 * B_HB);
        }
#pragma unroll
        for (int c = 0; c < 4; c++) mbar_expect_tx(bars + 8 * (B_U + c), c < 3 ? U_BYTES : 2 * U_BYTES);
        const uint4* usrc = g_U + 5 * b * U_PITCH;
        mbar_wait(bars + 8 * B_USIG, 0);
        flag_wait(g_cnt + C_PREP + 32 * (b & 15), (epoch + 1) * NCTA);
        TS(23);
#pragma unroll
        for (int c = 0; c < 5; c++) {
          if (c == 3) mbar_wait(bars + 8 * (B_U + 2), 0);
          bulk_load(sb + off_ch(c), usrc + c * U_PITCH, U_BYTES, bars + 8 * (B_U + (c < 3 ? c : 3)));
          TSIF(c == 0 || c == 4, 116 + (c >> 2));
        }
      }
      epoch = __shfl_sync(0xffffffffu, epoch, 0);
      if (lane < 8) {
        const int src = (b & ~7) | step_src(hg, lane);
        mbar_wait(bars + 8 * B_OSIG, 0);
        flag_wait(g_cnt + C_O + 32 * src, epoch + 1);
        if (lane >= 1 && lane < 4) bulk_load(sb + off_o(lane), g_O + src * 1280, O_BYTES, bars + 8 * (B_FULL2 + lane));
        __syncwarp(0xff);
        TS(21);
        if (lane == 5) bulk_load(sb + OFF_GATE, g_gate + 128 * r, 512, bars + 8 * (B_FULL2 + 5));
#pragma unroll 1
        for (int j = 4; j < 8; j++) {
          if (lane == j) {
            mbar_wait(bars + 8 * (j < 6 ? B_C34 : B_EMPTY2 + j - 6), 0);
            if (RF_GATE && j == 6) mbar_wait(bars + 8 * B_YSIG, 0);
            bulk_load(sb + off_o(j), g_O + src * 1280, O_BYTES, bars + 8 * (B_FULL2 + j));
          }
          __syncwarp(0xff);
        }
        TS(22);
      }
    } else if (w == 2) {
      mbar_wait(bars + 8 * B_PREP, 0);
      flag_signal(g_cnt + C_PREP, 16, lane);
      TS(25);
      if (lane == 0) mbar_arrive(bars + 8 * B_USIG);
      mbar_wait(bars + 8 * B_GATE, 0);
      if ((NOMB & 1) && lane == 0) asm volatile("fence.release.gpu;" ::: "memory");
      mbar_wait(bars + 8 * B_ATTN, 0);
      if (lane == 0) {
        if (O_DEFER) mbar_wait(bars + 8 * (B_U + 3), 0);
        asm volatile("cp.async.bulk.global.shared::cta.bulk_group [%0], [%1], 20480;\ncp.async.bulk.commit_group;\n"
                     "cp.async.bulk.wait_group 0;\nfence.proxy.async.global;" ::"l"(g_O + b * 1280), "r"(sb + OFF_OA) : "memory");
      }
      TS(74);
      if (!(NOMB & 1)) flag_signal(g_cnt + C_O + 32 * b, 1, lane);
      else if (lane == 0) flag_bump(g_cnt + C_O + 32 * b);
      TS(26);
      if (lane == 0) mbar_arrive(bars + 8 * B_OSIG);

    } else {
      {
        uint4* dst = g_WO + (hg * 8 + (r >> 1)) * 800 + (r & 1) * 80;
        const uint4* src = reinterpret_cast<const uint4*>(p.wo) + 40 * r * 80 + 10 * hg;
        mbar_wait(bars + 8 * WP_TRIG, 0);
#pragma unroll 1
        for (int i0 = 0; i0 < 400; i0 += 160) {
          uint4 v[5];
#pragma unroll
          for (int j = 0; j < 5; j++) {
            const int i = i0 + 32 * j + lane, n = i / 80, row = (i - 80 * n) >> 1;
            if (i < 400) v[j] = ldg128(src + row * 80 + 2 * n + ((i ^ (row >> 2)) & 1));
          }
#pragma unroll
          for (int j = 0; j < 5; j++) {
            const int i = i0 + 32 * j + lane;
            if (i < 400) dst[i + 80 * (i / 80)] = v[j];
          }
        }
        __syncwarp();
        flag_signal(g_cnt + C_W + 32 * hg, 1, lane);
      }
      if (lane == 0) {
        mbar_arrive(bars + 8 * B_WOP);
        TS(71);
#pragma unroll 1
        for (int c = 0; c < 5; c++) {
          mbar_wait(bars + 8 * (B_YST + c), 0);
          asm volatile("cp.async.bulk.global.shared::cta.bulk_group [%0], [%1], 4096;\ncp.async.bulk.commit_group;"
                       ::"l"(g_Y + (5 * b + c) * Y_PITCH), "r"(sb + off_ch(c)) : "memory");
          if (c == 2) {
            asm volatile("cp.async.bulk.wait_group.read 0;" ::: "memory");
            mbar_arrive(bars + 8 * B_C34);
          }
        }
        asm volatile("cp.async.bulk.wait_group 0;\nfence.proxy.async.global;" ::: "memory");
        TS(75);
        if (!(NOMB & 2)) asm volatile("fence.release.gpu;" ::: "memory");
        flag_bump(g_cnt + C_Y + 32 * (b >> 4));
        TS(27);
        mbar_arrive(bars + 8 * B_YSIG);
        mbar_expect_tx(bars + 8 * B_YFULL, 20480);
        flag_wait(g_cnt + C_Y + 32 * hg, (lds32(sb + OFF_EPOCH) + 1) * 16);
        TS(24);
        tma_2d(sb + OFF_YT, &m.y, 128 * r, 80 * hg, bars + 8 * B_YFULL);
        tma_2d(sb + OFF_YT + 10240, &m.y, 128 * r + 64, 80 * hg, bars + 8 * B_YFULL);
      }
    }
  } else {
    asm volatile("setmaxnreg.inc.sync.aligned.u32 152;");
    if (wg < 2) {
      float acc[120];
#pragma unroll
      for (int i = 0; i < 120; i++) acc[i] = 0.f;
      const uint32_t da = desc_lo(sb + wg * 8192, 16), db = desc_lo(sb + ST_W, 8192), dc = desc_lo(sb + ST_WT, 2048);
      if (PW1) pin<120>(acc);
      if (PW1 == 2) mbar_wait(bars + 8 * B_FULL1, 0);
#pragma unroll 1
      for (int kb = 0; kb < 10; kb++) {
        mbar_wait(bars + 8 * (B_FULL1 + (kb & 3)), (kb >> 2) & 1);
        const uint32_t so = (kb & 3) * (STAGE_BYTES >> 4);
        wg_fence();
#pragma unroll
        for (int k = 0; k < 4; k++) {
          WgSST<192>::mma<HI_SW128, HI_SW128>(acc, da + so + 2 * k, db + so + 128 * k, 1);
          WgSST<48>::mma<HI_SW128, HI_SW32>(acc + 96, da + so + 2 * k, dc + so + 32 * k, 1);
        }
        wg_commit();
        wg_wait<1>();
        if (kb > 0 && lane == 0) mbar_arrive(bars + 8 * (kb == 4 ? B_E3 : B_EMPTY1 + ((kb - 1) & 3)));
      }
      wg_wait<0>();
      pin<120>(acc);
      if (lane == 0) mbar_arrive(bars + 8 * B_P1);
      TSM(w == 0, 3 + wg);
      attention(acc, sb, b, wg, w, lane);
    } else {
      const int tw = tid & 127, chl = 64 * (b & 1) + 8 * w + (lane >> 2);
      uint4* up = g_U + chl * U_PITCH + ((4 * (b >> 1) + (lane & 3)) ^ ((b >> 2) & 1));
      uint2 sw[10];
      uint32_t dv = 0;
      if (lane < 5) dv = __ldg(reinterpret_cast<const unsigned short*>(p.ssm_D) + 5 * b + lane);
#pragma unroll
      for (int i = 0; i < 10; i++) sw[i] = ldg64(reinterpret_cast<const uint2*>(p.shift_k) + chl + 128 * (i >> 1) + 32 * (i & 1));
      uint32_t tab[12];
      fft_tables(tab, tw);
      uint4 res[10];
#pragma unroll
      for (int i = 0; i < 10; i++) res[i] = make_uint4(0, 0, 0, 0);
#pragma unroll 1
      for (int slab = 0; slab < 5; slab++) {
#pragma unroll
        for (int i = 0; i < 8; i++) res[i] = res[i + 2];
        prep_slab(res + 8, sw, sb, slab, w, lane);
        TSIF(w == 0, 99 + 4 * slab);
#pragma unroll
        for (int i = 0; i < 8; i++) sw[i] = sw[i + 2];
      }
      TSIF(w == 0, 28);
      __syncwarp();
      if (lane == 0) mbar_arrive(bars + 8 * B_KVD + ((res[8].x ^ res[9].x) & p.zero));
      mbar_wait(bars + 8 * B_KVD, 0);
      fft_tables_store(tab, sb, tw);
      mbar_wait(bars + 8 * B_LAST, 0);
#pragma unroll
      for (int i = 0; i < 10; i++) up[(128 * (i >> 1) + 32 * (i & 1)) * U_PITCH] = res[i];
      __syncwarp();
      if (lane == 0) mbar_arrive(bars + 8 * B_PREP);
      TSIF(w == 0, 5);
      mbar_wait(bars + 8 * (G_AFTER ? B_USIG : B_LAST), 0);
      prep_gate(p, b, w, lane);
      __syncwarp();
      if (lane == 0) mbar_arrive(bars + 8 * B_GATE);
      TSIF(w == 0, 72);
      mbar_wait(bars + 8 * B_HB, 0);
      TSIF(w == 0, 123);
      const uint32_t ha = sb + U_BYTES + ((tw >> 3) * 16 + 8 + (tw & 7)) * 16;
      uint4 hv[5];
#pragma unroll
      for (int c = 0; c < 5; c++) hv[c] = lds128(ha + off_ch(c));
      __syncwarp();
#pragma unroll
      for (int c = 0; c < 5; c++) sts128((ha ^ 16) + off_ch(c), hv[c].x, hv[c].y, hv[c].z, hv[c].w);
      if (tw < 5) asm volatile("st.shared.f32 [%0], %1;" ::"r"(sb + OFF_D + 4 * tw), "f"(bf_lo(dv) * 0.125f) : "memory");
      fence_async_smem();
      __syncwarp();
      if (lane == 0) mbar_arrive(bars + 8 * B_HA);
      TSIF(w == 0, 6);
    }

    FftConst fc;
    fft_twiddles(fc, w, lane);
    mbar_wait(bars + 8 * B_HA, 0);
    fft_matrices(fc, sb, w, lane);
    if (ATT_GATE && !H_EARLY) mbar_wait(bars + 8 * B_ATTN, 0);
    TSIF(w == 0 && wg == 2, 124);
#pragma unroll 1
    for (int c = wg == 2 ? 0 : wg + 1; c < 5; c += 3) {
      conv_channel(fc, sb, c, wg, w, lane);
      if (lane == 0) mbar_arrive(bars + 8 * (B_YST + c));
      TSM(w == 0, 10 + c);
    }

    if (wg < 2) {
      const int g = lane >> 2;
      float acc[40];
#pragma unroll
      for (int i = 0; i < 40; i++) acc[i] = 0.f;
      const uint32_t da = desc_lo(sb + wg * 1024, 2048), db = desc_lo(sb, 2560);
      mbar_wait(bars + 8 * B_ATTN, 0);
      mbar_wait(bars + 8 * (B_YST + 3), 0);
      mbar_wait(bars + 8 * (B_YST + 4), 0);
      if (PW2) mbar_wait(bars + 8 * B_FULL2, 0);
#pragma unroll 1
      for (int j = 0; j < 8; j++) {
        mbar_wait(bars + 8 * (B_FULL2 + j), 0);
        const uint32_t oa = da + (off_o(j) >> 4), ob = db + (off_w(j) >> 4);
        wg_fence();
#pragma unroll
        for (int k = 0; k < 5; k++) WgSST<80>::mma<HI_NONE, HI_SW32>(acc, oa + 256 * k, ob + 32 * k, 1);
        wg_commit();
        wg_wait<1>();
        if (j >= 1 && j <= 4 && lane == 0) mbar_arrive(bars + 8 * (B_EMPTY2 + j - 1));
      }
      TSIF(w == 0 && wg == 0, 113);
      const int tr = 64 * wg + 16 * w + (lane & 15);
      const uint32_t fm = sb + OFF_QS + tr * 128, fx = (lane >> 4) ^ (tr & 7);
      const uint32_t ft = sb + OFF_QT + tr * 32 + (((lane >> 4) ^ (tr >> 2)) & 1) * 16;
      const float g0 = __uint_as_float(lds32(sb + OFF_GATE + (64 * wg + 16 * w + g) * 4));
      const float g1 = __uint_as_float(lds32(sb + OFF_GATE + (64 * wg + 16 * w + 8 + g) * 4));
      const uint32_t ga = pack2(g0, g0), gb = pack2(g1, g1);
      const uint32_t na = pack2(1.f - g0, 1.f - g0), nb = pack2(1.f - g1, 1.f - g1);

      wg_wait<0>();
      pin<40>(acc);
      TSM(w == 0, 17 + wg);
      uint32_t pb[20];
#pragma unroll
      for (int j = 0; j < 10; j++) {
        pb[2 * j] = bmul(na, pack2(acc[4 * j], acc[4 * j + 1]));
        pb[2 * j + 1] = bmul(nb, pack2(acc[4 * j + 2], acc[4 * j + 3]));
        asm volatile("" : "+r"(pb[2 * j]), "+r"(pb[2 * j + 1]));
      }
      const uint32_t ya = sb + OFF_YT + wg * 10240 + ((lane >> 4) * 8 + (lane & 7)) * 128 +
                          (((2 * w + (((lane >> 3) & 1) ^ wg)) ^ (lane & 7)) << 4);
      uint32_t qf[20];
      mbar_wait(bars + 8 * B_QF, 0);
#pragma unroll
      for (int j = 0; j < 5; j++) ldsm4(qf + 4 * j, j < 4 ? fm + ((fx ^ (2 * j)) << 4) : ft);
      mbar_wait(bars + 8 * B_YFULL, 0);
      TSIF(w == 0 && wg == 0, 19);
#pragma unroll
      for (int j = 0; j < 5; j++) {
        uint32_t y[4];
        ldsm4t(y, ya + 2048 * j);
#pragma unroll
        for (int i = 0; i < 4; i++) qf[4 * j + i] = badd(bmul((i & 1) ? gb : ga, bmul(qf[4 * j + i], y[i])), pb[4 * j + i]);
      }
#pragma unroll
      for (int j = 0; j < 5; j++) stsm4(j < 4 ? fm + ((fx ^ (2 * j)) << 4) : ft, qf + 4 * j);
      fence_async_smem();
      __syncwarp();
      if (lane == 0) {
        const int row = 64 * wg + 16 * w;
        asm volatile("cp.async.bulk.tensor.2d.global.shared::cta.bulk_group [%0, {%2, %3}], [%1];"
                     ::"l"(&m.om), "r"(sb + OFF_QS + row * 128), "r"(80 * hg), "r"(128 * r + row) : "memory");
        asm volatile("cp.async.bulk.tensor.2d.global.shared::cta.bulk_group [%0, {%2, %3}], [%1];"
                     ::"l"(&m.ot), "r"(sb + OFF_QT + row * 32), "r"(80 * hg + 64), "r"(128 * r + row) : "memory");
        asm volatile("cp.async.bulk.commit_group;\ncp.async.bulk.wait_group.read 0;" ::: "memory");
      }
      TSM(true, 40 + 4 * wg + w);
      if (ENDBAR) asm volatile("bar.sync 15, 256;" ::: "memory");
    }
  }
}

typedef CUresult (*EncodeFn)(CUtensorMap*, CUtensorMapDataType, cuuint32_t, void*, const cuuint64_t*, const cuuint64_t*,
                             const cuuint32_t*, const cuuint32_t*, CUtensorMapInterleave, CUtensorMapSwizzle,
                             CUtensorMapL2promotion, CUtensorMapFloatOOBfill);

void encode(EncodeFn fn, CUtensorMap* tm, const void* base, int rank, const cuuint64_t* dims, const cuuint64_t* strides,
            const cuuint32_t* box, CUtensorMapSwizzle swz) {
  const cuuint32_t ones[3] = {1, 1, 1};
  fn(tm, CU_TENSOR_MAP_DATA_TYPE_BFLOAT16, rank, const_cast<void*>(base), dims, strides, box, ones,
     CU_TENSOR_MAP_INTERLEAVE_NONE, swz, CU_TENSOR_MAP_L2_PROMOTION_L2_128B, CU_TENSOR_MAP_FLOAT_OOB_FILL_NONE);
}

}

extern "C" void kernel_launch(void* const* d_in, const int* in_sizes, int n_in, void* d_out, int out_size) {
  (void)in_sizes; (void)n_in; (void)out_size;
  Params p;
  p.q = (const __nv_bfloat16*)d_in[0];
  p.k = (const __nv_bfloat16*)d_in[1];
  p.v = (const __nv_bfloat16*)d_in[2];
  p.shift_k = (const __nv_bfloat16*)d_in[3];
  p.ssm_k = (const __nv_bfloat16*)d_in[4];
  p.ssm_D = (const __nv_bfloat16*)d_in[5];
  p.wqkv = (const __nv_bfloat16*)d_in[7];
  p.wo = (const __nv_bfloat16*)d_in[8];
  p.gate_w = (const __nv_bfloat16*)d_in[9];
  p.out = (__nv_bfloat16*)d_out;
  p.zero = 0;

  static EncodeFn fn = nullptr;
  static void* yaddr = nullptr;
  if (!fn) {
    cudaDriverEntryPointQueryResult qr;
    void* f = nullptr;
    cudaGetDriverEntryPoint("cuTensorMapEncodeTiled", &f, cudaEnableDefault, &qr);
    fn = (EncodeFn)f;
    cudaGetSymbolAddress(&yaddr, g_Y);
    cudaFuncSetAttribute(fused_kernel, cudaFuncAttributeMaxDynamicSharedMemorySize, SMEM_BYTES);
  }
  Maps m;
  {
    const cuuint64_t dims[3] = {640, 1024, 2}, st[2] = {2560, 1280};
    const cuuint32_t box[3] = {64, 64, 2};
    encode(fn, &m.x, p.q, 3, dims, st, box, CU_TENSOR_MAP_SWIZZLE_128B);
  }
  {
    const cuuint64_t dims[3] = {640, 640, 3}, st[2] = {3840, 1280};
    const cuuint32_t box[3] = {64, 64, 3}, boxt[3] = {16, 64, 3};
    encode(fn, &m.wm, p.wqkv, 3, dims, st, box, CU_TENSOR_MAP_SWIZZLE_128B);
    encode(fn, &m.wt, p.wqkv, 3, dims, st, boxt, CU_TENSOR_MAP_SWIZZLE_32B);
  }
  {
    const cuuint64_t dims[3] = {64, 2048, 10}, st[2] = {1280, 128};
    const cuuint32_t boxk[3] = {64, 35, 1}, boxv[3] = {64, 32, 1};
    encode(fn, &m.k, p.k, 3, dims, st, boxk, CU_TENSOR_MAP_SWIZZLE_128B);
    encode(fn, &m.v, p.v, 3, dims, st, boxv, CU_TENSOR_MAP_SWIZZLE_128B);
  }
  {
    const cuuint64_t dims[3] = {16, 640, 40}, st[2] = {1280, 32};
    const cuuint32_t box[3] = {16, 40, 5};
    encode(fn, &m.wo, p.wo, 3, dims, st, box, CU_TENSOR_MAP_SWIZZLE_32B);
  }
  {
    const cuuint64_t dims[2] = {2048, 640}, st[1] = {Y_PITCH * 16};
    const cuuint32_t box[2] = {64, 80};
    encode(fn, &m.y, yaddr, 2, dims, st, box, CU_TENSOR_MAP_SWIZZLE_128B);
  }
  {
    const cuuint64_t dims[2] = {640, 2048}, st[1] = {1280};
    const cuuint32_t bqm[2] = {64, 128}, bqt[2] = {16, 128}, bom[2] = {64, 16}, bot[2] = {16, 16};
    encode(fn, &m.qm, p.q, 2, dims, st, bqm, CU_TENSOR_MAP_SWIZZLE_128B);
    encode(fn, &m.qt, p.q, 2, dims, st, bqt, CU_TENSOR_MAP_SWIZZLE_32B);
    encode(fn, &m.om, p.out, 2, dims, st, bom, CU_TENSOR_MAP_SWIZZLE_128B);
    encode(fn, &m.ot, p.out, 2, dims, st, bot, CU_TENSOR_MAP_SWIZZLE_32B);
  }
  fused_kernel<<<NCTA, NTHR, SMEM_BYTES>>>(m, p);
}
```

```cpp
#include <cuda.h>
#include <cuda_bf16.h>
#include <cuda_runtime.h>
#include <stdint.h>

namespace {

constexpr int SEQ = 2048, DIM = 640, NCTA = 128, NTHR = 512;

#define TRIG_KB 9
#define KV_KB 2
#define DEV_EXIT 0
#define ATT_GATE 1
#define G_AFTER 0
#define FENCE_LO 0
#define FENCE_HI 0
#define PW1 2
#define PW2 1
#define ENDBAR 0
#define PAD_KB 0
#define Y_ALIAS 1
#define H_EARLY 1
#define WO_LSU 0
#define WP_TRIG (B_KV + 4)
#define NOMB 0
#define SRC_ROT 0
#define WAIT_NS 0
#define WB_TRIG B_USIG
#define G_POS 0
#define TAILF 1
#define T_ISSUE 384
#define T_PF 416
#define T_INIT 448
#define ATT_MERGE 0
#define BMAP 1
#define PRE2 1
#define KV_MIX 0
#define O_DEFER 0
#define TOK_G 1
#define RF_GATE 0
#define WO_TRIG B_WST
#define WL_TRIG B_WOP
#define WO_GATE 1

constexpr uint32_t STAGE_BYTES = 47104, ST_W = 16384, ST_WT = 40960;
constexpr uint32_t O_BYTES = 20480, WO_BYTES = 12800;
constexpr uint32_t OFF_OA = 0;
constexpr uint32_t OFF_QS = 3 * O_BYTES, OFF_QT = OFF_QS + 16384;
constexpr uint32_t OFF_WC = 81920;
constexpr uint32_t OFF_WA = 94720;
constexpr uint32_t OFF_GATE = 145920;
constexpr uint32_t OFF_KVX = 147968;
constexpr uint32_t OFF_D = OFF_GATE + 512;
constexpr uint32_t OFF_CH3 = 163840;
constexpr uint32_t CH_BYTES = 12288, U_BYTES = 4096;
constexpr uint32_t OFF_FT = 225280, OFF_GT = 229376;
constexpr uint32_t OFF_CH0 = 188416;
constexpr uint32_t OFF_KVS = OFF_CH0, KVS_V = 4480, KVS_BYTES = 8576;
constexpr uint32_t OFF_WS = OFF_WA;
constexpr uint32_t OFF_YT = 163840;
constexpr uint32_t OFF_BAR = 231936;
constexpr uint32_t SMEM_BYTES = OFF_BAR + 512;

enum : uint32_t {
  B_FULL1 = 0, B_EMPTY1 = 4, B_S3 = 7, B_FULL2 = 52, B_EMPTY2 = 13, B_U = 8, B_GATE = 12, B_HA = 19, B_HB = 20,
  B_ATTN = 21, B_C34 = 22, B_CONV = 23, B_YFULL = 24, B_EPOCH = 25, B_PREP = 26, B_P1 = 27, B_LAST = 28,
  B_E3 = 29, B_OSIG = 30, B_WOP = 31, B_USIG = 32, B_WST = 33, B_KV = 34, B_KVD = 39, B_HC = 61, B_QF = 62, B_YST = 40,
  B_TOK = 45, B_YSIG = 50
};
constexpr uint32_t OFF_EPOCH = OFF_BAR + 8 * 51;
__device__ __forceinline__ uint32_t off_o(int j) { return j < 4 ? OFF_OA + j * O_BYTES : j < 6 ? OFF_CH0 + (j - 4) * O_BYTES : OFF_OA + (j - 6) * O_BYTES; }
__device__ __forceinline__ uint32_t off_w(int j) { return j < 4 ? OFF_WA + j * WO_BYTES : j == 4 ? OFF_KVX : j == 5 ? OFF_WC : OFF_WA + (j - 6) * WO_BYTES; }
__device__ __forceinline__ int step_src(int hg, int j) { return SRC_ROT ? (hg + j) & 7 : j == 0 ? hg : j <= hg ? j - 1 : j; }
__device__ __forceinline__ bool tail_first(int hg) { return TAILF && (hg & 3) == 3; }
__device__ __forceinline__ uint32_t off_ch(int c) { return (c < 3 ? OFF_CH0 : OFF_CH3 - 3 * CH_BYTES) + c * CH_BYTES; }

#define U_PITCH 264
__device__ __align__(1024) uint4 g_U[DIM * U_PITCH];
__device__ uint4 g_O[NCTA * 1280];
#define g_Y g_U
constexpr int Y_PITCH = U_PITCH;
__device__ uint4 g_WO[64 * 800];
__device__ uint4 g_halo[NCTA * 2 * 7 * 32];
__device__ float g_gate[SEQ + PAD_KB * 256];
__device__ unsigned g_cnt[32 * (1 + 2 * 16 + 8 + NCTA)];
constexpr int C_LAUNCH = 0, C_PREP = 32, C_Y = 32 * 17, C_W = 32 * 33, C_O = 32 * 41;

#define TSM(cond, slot) do { } while (0)
#define TSIF(cond, slot) do { if (__LINE__ >= FENCE_LO && __LINE__ < FENCE_HI) sched_fence(); } while (0)
__device__ __forceinline__ void sched_fence() {
  asm volatile("{\n.reg .pred p;\n.reg .u32 c;\nmov.u32 c, %%clock;\nsetp.eq.u32 p, c, 0;\n@p st.shared.u32 [%0], c;\n}"
               ::"r"(1024 + OFF_EPOCH + 4) : "memory");
}
#define TS(slot) TSIF(true, slot)

struct Params {
  const __nv_bfloat16 *q, *k, *v, *shift_k, *ssm_k, *ssm_D, *wqkv, *wo, *gate_w;
  __nv_bfloat16* out;
  uint32_t zero;
};

#define POLL_NS 0
constexpr int SPIN_LIMIT = 1 << 17;

__device__ __forceinline__ void mbar_init(uint32_t bar, uint32_t count) {
  asm volatile("mbarrier.init.shared::cta.b64 [%0], %1;" ::"r"(bar), "r"(count) : "memory");
}
__device__ __forceinline__ void mbar_expect_tx(uint32_t bar, uint32_t bytes) {
  asm volatile("mbarrier.arrive.expect_tx.shared::cta.b64 _, [%0], %1;" ::"r"(bar), "r"(bytes) : "memory");
}
__device__ __forceinline__ void mbar_arrive(uint32_t bar) {
  asm volatile("mbarrier.arrive.shared::cta.b64 _, [%0];" ::"r"(bar) : "memory");
}
__device__ __forceinline__ void mbar_wait(uint32_t bar, uint32_t parity) {
  uint32_t ok;
  int spins = 0;
  do {
    if (WAIT_NS)
      asm volatile("{\n.reg .pred p;\nmbarrier.try_wait.parity.shared::cta.b64 p, [%1], %2, %3;\nselp.b32 %0, 1, 0, p;\n}"
                   : "=r"(ok) : "r"(bar), "r"(parity), "r"(WAIT_NS) : "memory");
    else
      asm volatile("{\n.reg .pred p;\nmbarrier.try_wait.parity.shared::cta.b64 p, [%1], %2;\nselp.b32 %0, 1, 0, p;\n}"
                   : "=r"(ok) : "r"(bar), "r"(parity) : "memory");
    if (++spins > SPIN_LIMIT) break;
  } while (!ok);
}
__device__ __forceinline__ void flag_poll(const unsigned* p, unsigned target) {
  unsigned v;
  int spins = 0;
  do {
    if (POLL_NS && spins) __nanosleep(POLL_NS);
    asm volatile("ld.relaxed.gpu.global.u32 %0, [%1];" : "=r"(v) : "l"(p) : "memory");
    if (++spins > SPIN_LIMIT) break;
  } while ((int)(v - target) < 0);
}
__device__ __forceinline__ void flag_wait(const unsigned* p, unsigned target) {
  flag_poll(p, target);
  asm volatile("fence.acquire.gpu;\nfence.proxy.async.global;" ::: "memory");
}
__device__ __forceinline__ void flag_signal(unsigned* p, int n, int lane) {
  if (lane == 0) asm volatile("fence.release.gpu;" ::: "memory");
  __syncwarp();
  if (lane < n) asm volatile("red.relaxed.gpu.global.add.u32 [%0], 1;" ::"l"(p + 32 * lane) : "memory");
}
__device__ __forceinline__ void flag_bump(unsigned* p) {
  asm volatile("red.relaxed.gpu.global.add.u32 [%0], 1;" ::"l"(p) : "memory");
}
__device__ __forceinline__ void fence_async_smem() { asm volatile("fence.proxy.async.shared::cta;" ::: "memory"); }
__device__ __forceinline__ void wg_sync(int id) { asm volatile("bar.sync %0, 128;" ::"r"(id) : "memory"); }

__device__ __forceinline__ void tma_2d(uint32_t dst, const CUtensorMap* tm, int c0, int c1, uint32_t bar) {
  asm volatile("cp.async.bulk.tensor.2d.shared::cluster.global.mbarrier::complete_tx::bytes [%0], [%1, {%3, %4}], [%2];"
               ::"r"(dst), "l"(tm), "r"(bar), "r"(c0), "r"(c1) : "memory");
}
__device__ __forceinline__ void tma_3d(uint32_t dst, const CUtensorMap* tm, int c0, int c1, int c2, uint32_t bar) {
  asm volatile("cp.async.bulk.tensor.3d.shared::cluster.global.mbarrier::complete_tx::bytes [%0], [%1, {%3, %4, %5}], [%2];"
               ::"r"(dst), "l"(tm), "r"(bar), "r"(c0), "r"(c1), "r"(c2) : "memory");
}
__device__ __forceinline__ void bulk_load(uint32_t dst, const void* src, uint32_t bytes, uint32_t bar) {
  asm volatile("cp.async.bulk.shared::cluster.global.mbarrier::complete_tx::bytes [%0], [%1], %2, [%3];"
               ::"r"(dst), "l"(src), "r"(bytes), "r"(bar) : "memory");
}
__device__ __forceinline__ void tm_prefetch(const CUtensorMap* tm) {
  asm volatile("prefetch.tensormap [%0];" ::"l"(tm) : "memory");
}

__device__ __forceinline__ void wg_fence() { asm volatile("wgmma.fence.sync.aligned;" ::: "memory"); }
__device__ __forceinline__ void wg_commit() { asm volatile("wgmma.commit_group.sync.aligned;" ::: "memory"); }
template <int N> __device__ __forceinline__ void wg_wait() { asm volatile("wgmma.wait_group.sync.aligned %0;" ::"n"(N) : "memory"); }
__device__ __forceinline__ uint32_t desc_lo(uint32_t addr, uint32_t lbo) { return ((addr & 0x3FFFF) >> 4) | ((lbo >> 4) << 16); }
constexpr uint32_t desc_hi(uint32_t sbo, uint32_t swz) { return (sbo >> 4) | (swz << 30); }
constexpr uint32_t HI_SW128 = desc_hi(1024, 1), HI_SW64 = desc_hi(512, 2), HI_SW32 = desc_hi(256, 3), HI_NONE = desc_hi(128, 0);
template <int N> __device__ __forceinline__ void pin(float* d) {
#pragma unroll
  for (int i = 0; i < N; i++) asm volatile("" : "+f"(d[i])::"memory");
}

__device__ __forceinline__ uint32_t lds32(uint32_t a) {
  uint32_t v;
  asm volatile("ld.volatile.shared.u32 %0, [%1];" : "=r"(v) : "r"(a) : "memory");
  return v;
}
__device__ __forceinline__ uint4 ldg128(const void* a) {
  uint4 v;
  asm volatile("ld.global.nc.v4.u32 {%0, %1, %2, %3}, [%4];" : "=r"(v.x), "=r"(v.y), "=r"(v.z), "=r"(v.w) : "l"(a) : "memory");
  return v;
}
__device__ __forceinline__ uint2 ldg64(const void* a) {
  uint2 v;
  asm volatile("ld.global.nc.v2.u32 {%0, %1}, [%2];" : "=r"(v.x), "=r"(v.y) : "l"(a) : "memory");
  return v;
}
__device__ __forceinline__ void ldsm4(uint32_t* r, uint32_t a) {
  asm volatile("ldmatrix.sync.aligned.m8n8.x4.shared.b16 {%0, %1, %2, %3}, [%4];"
               : "=r"(r[0]), "=r"(r[1]), "=r"(r[2]), "=r"(r[3]) : "r"(a) : "memory");
}
__device__ __forceinline__ void ldsm4t(uint32_t* r, uint32_t a) {
  asm volatile("ldmatrix.sync.aligned.m8n8.x4.trans.shared.b16 {%0, %1, %2, %3}, [%4];"
               : "=r"(r[0]), "=r"(r[1]), "=r"(r[2]), "=r"(r[3]) : "r"(a) : "memory");
}
__device__ __forceinline__ uint4 lds128(uint32_t a) {
  uint4 v;
  asm volatile("ld.shared.v4.u32 {%0, %1, %2, %3}, [%4];" : "=r"(v.x), "=r"(v.y), "=r"(v.z), "=r"(v.w) : "r"(a) : "memory");
  return v;
}
__device__ __forceinline__ void sts128(uint32_t a, uint32_t x, uint32_t y, uint32_t z, uint32_t w) {
  asm volatile("st.shared.v4.u32 [%0], {%1, %2, %3, %4};" ::"r"(a), "r"(x), "r"(y), "r"(z), "r"(w) : "memory");
}
__device__ __forceinline__ void stsm4(uint32_t a, const uint32_t* r) {
  asm volatile("stmatrix.sync.aligned.m8n8.x4.shared.b16 [%0], {%1, %2, %3, %4};" ::"r"(a), "r"(r[0]), "r"(r[1]), "r"(r[2]), "r"(r[3]) : "memory");
}
__device__ __forceinline__ void stsm4t(uint32_t a, const uint32_t* r) {
  asm volatile("stmatrix.sync.aligned.m8n8.x4.trans.shared.b16 [%0], {%1, %2, %3, %4};" ::"r"(a), "r"(r[0]), "r"(r[1]), "r"(r[2]), "r"(r[3]) : "memory");
}
__device__ __forceinline__ uint32_t pack2(float lo, float hi) {
  uint32_t r;
  asm("cvt.rn.bf16x2.f32 %0, %1, %2;" : "=r"(r) : "f"(hi), "f"(lo));
  return r;
}
__device__ __forceinline__ uint32_t movm(uint32_t a) {
  uint32_t d;
  asm volatile("movmatrix.sync.aligned.m8n8.trans.b16 %0, %1;" : "=r"(d) : "r"(a));
  return d;
}
__device__ __forceinline__ uint32_t bmul(uint32_t a, uint32_t b) {
  uint32_t d;
  asm("mul.rn.bf16x2 %0, %1, %2;" : "=r"(d) : "r"(a), "r"(b));
  return d;
}
__device__ __forceinline__ uint32_t badd(uint32_t a, uint32_t b) {
  uint32_t d;
  asm("add.rn.bf16x2 %0, %1, %2;" : "=r"(d) : "r"(a), "r"(b));
  return d;
}
__device__ __forceinline__ float bf_lo(uint32_t x) { return __uint_as_float(x << 16); }
__device__ __forceinline__ float bf_hi(uint32_t x) { return __uint_as_float(x & 0xFFFF0000u); }
__device__ __forceinline__ float ex2(float x) {
  float y;
  asm("ex2.approx.ftz.f32 %0, %1;" : "=f"(y) : "f"(x));
  return y;
}
__device__ __forceinline__ float rcp(float x) {
  float y;
  asm("rcp.approx.ftz.f32 %0, %1;" : "=f"(y) : "f"(x));
  return y;
}
__device__ __forceinline__ void mma16816(float* d, uint32_t a0, uint32_t a1, uint32_t a2, uint32_t a3, uint32_t b0, uint32_t b1) {
  asm volatile("mma.sync.aligned.m16n8k16.row.col.f32.bf16.bf16.f32 {%0, %1, %2, %3}, {%4, %5, %6, %7}, {%8, %9}, {%0, %1, %2, %3};"
               : "+f"(d[0]), "+f"(d[1]), "+f"(d[2]), "+f"(d[3])
               : "r"(a0), "r"(a1), "r"(a2), "r"(a3), "r"(b0), "r"(b1));
}
__device__ __forceinline__ void mma1688(float* d, uint32_t a0, uint32_t a1, uint32_t b0) {
  asm volatile("mma.sync.aligned.m16n8k8.row.col.f32.bf16.bf16.f32 {%0, %1, %2, %3}, {%4, %5}, {%6}, {%0, %1, %2, %3};"
               : "+f"(d[0]), "+f"(d[1]), "+f"(d[2]), "+f"(d[3])
               : "r"(a0), "r"(a1), "r"(b0));
}

template <int N> struct WgRS;
template <int N> struct WgSST;
template <> struct WgRS<32> {
  template <uint32_t HB>
  static __device__ __forceinline__ void mma(float* d, const uint32_t* a, uint32_t db) {
    asm volatile("{\n.reg .pred p;\n.reg .b64 db;\nsetp.ne.b32 p, %22, 0;\n"
      "mov.b64 db, {%20, %21};\n"
      "wgmma.mma_async.sync.aligned.m64n32k16.f32.bf16.bf16 {"
      "%0, %1, %2, %3, %4, %5, %6, %7, %8, %9, %10, %11, %12, %13, %14, %15"
      "}, {%16, %17, %18, %19}, db, p, 1, 1, 1;\n}\n"
      : "+f"(d[0]), "+f"(d[1]), "+f"(d[2]), "+f"(d[3]), "+f"(d[4]), "+f"(d[5]), "+f"(d[6]), "+f"(d[7]),
        "+f"(d[8]), "+f"(d[9]), "+f"(d[10]), "+f"(d[11]), "+f"(d[12]), "+f"(d[13]), "+f"(d[14]), "+f"(d[15])
      : "r"(a[0]), "r"(a[1]), "r"(a[2]), "r"(a[3]), "r"(db), "n"(HB), "n"(1));
  }
  template <uint32_t HB>
  static __device__ __forceinline__ void set(float* d, const uint32_t* a, uint32_t db) {
    asm volatile("{\n.reg .pred p;\n.reg .b64 db;\nsetp.ne.b32 p, %22, 0;\n"
      "mov.b64 db, {%20, %21};\n"
      "wgmma.mma_async.sync.aligned.m64n32k16.f32.bf16.bf16 {"
      "%0, %1, %2, %3, %4, %5, %6, %7, %8, %9, %10, %11, %12, %13, %14, %15"
      "}, {%16, %17, %18, %19}, db, p, 1, 1, 1;\n}\n"
      : "=f"(d[0]), "=f"(d[1]), "=f"(d[2]), "=f"(d[3]), "=f"(d[4]), "=f"(d[5]), "=f"(d[6]), "=f"(d[7]),
        "=f"(d[8]), "=f"(d[9]), "=f"(d[10]), "=f"(d[11]), "=f"(d[12]), "=f"(d[13]), "=f"(d[14]), "=f"(d[15])
      : "r"(a[0]), "r"(a[1]), "r"(a[2]), "r"(a[3]), "r"(db), "n"(HB), "n"(0));
  }
};
template <> struct WgRS<64> {
  template <uint32_t HB>
  static __device__ __forceinline__ void mma(float* d, const uint32_t* a, uint32_t db) {
    asm volatile("{\n.reg .pred p;\n.reg .b64 db;\nsetp.ne.b32 p, %38, 0;\n"
      "mov.b64 db, {%36, %37};\n"
      "wgmma.mma_async.sync.aligned.m64n64k16.f32.bf16.bf16 {"
      "%0, %1, %2, %3, %4, %5, %6, %7, %8, %9, %10, %11, %12, %13, %14, %15, "
      "%16, %17, %18, %19, %20, %21, %22, %23, %24, %25, %26, %27, %28, %29, %30, %31"
      "}, {%32, %33, %34, %35}, db, p, 1, 1, 1;\n}\n"
      : "+f"(d[0]), "+f"(d[1]), "+f"(d[2]), "+f"(d[3]), "+f"(d[4]), "+f"(d[5]), "+f"(d[6]), "+f"(d[7]),
        "+f"(d[8]), "+f"(d[9]), "+f"(d[10]), "+f"(d[11]), "+f"(d[12]), "+f"(d[13]), "+f"(d[14]), "+f"(d[15]),
        "+f"(d[16]), "+f"(d[17]), "+f"(d[18]), "+f"(d[19]), "+f"(d[20]), "+f"(d[21]), "+f"(d[22]), "+f"(d[23]),
        "+f"(d[24]), "+f"(d[25]), "+f"(d[26]), "+f"(d[27]), "+f"(d[28]), "+f"(d[29]), "+f"(d[30]), "+f"(d[31])
      : "r"(a[0]), "r"(a[1]), "r"(a[2]), "r"(a[3]), "r"(db), "n"(HB), "n"(1));
  }
  template <uint32_t HB>
  static __device__ __forceinline__ void set(float* d, const uint32_t* a, uint32_t db) {
    asm volatile("{\n.reg .pred p;\n.reg .b64 db;\nsetp.ne.b32 p, %38, 0;\n"
      "mov.b64 db, {%36, %37};\n"
      "wgmma.mma_async.sync.aligned.m64n64k16.f32.bf16.bf16 {"
      "%0, %1, %2, %3, %4, %5, %6, %7, %8, %9, %10, %11, %12, %13, %14, %15, "
      "%16, %17, %18, %19, %20, %21, %22, %23, %24, %25, %26, %27, %28, %29, %30, %31"
      "}, {%32, %33, %34, %35}, db, p, 1, 1, 1;\n}\n"
      : "=f"(d[0]), "=f"(d[1]), "=f"(d[2]), "=f"(d[3]), "=f"(d[4]), "=f"(d[5]), "=f"(d[6]), "=f"(d[7]),
        "=f"(d[8]), "=f"(d[9]), "=f"(d[10]), "=f"(d[11]), "=f"(d[12]), "=f"(d[13]), "=f"(d[14]), "=f"(d[15]),
        "=f"(d[16]), "=f"(d[17]), "=f"(d[18]), "=f"(d[19]), "=f"(d[20]), "=f"(d[21]), "=f"(d[22]), "=f"(d[23]),
        "=f"(d[24]), "=f"(d[25]), "=f"(d[26]), "=f"(d[27]), "=f"(d[28]), "=f"(d[29]), "=f"(d[30]), "=f"(d[31])
      : "r"(a[0]), "r"(a[1]), "r"(a[2]), "r"(a[3]), "r"(db), "n"(HB), "n"(0));
  }
};
template <> struct WgSST<48> {
  template <uint32_t HA, uint32_t HB>
  static __device__ __forceinline__ void mma(float* d, uint32_t da, uint32_t db, int sc) {
    asm volatile("{\n.reg .pred p;\n.reg .b64 da, db;\nsetp.ne.b32 p, %28, 0;\n"
      "mov.b64 da, {%24, %25};\nmov.b64 db, {%26, %27};\n"
      "wgmma.mma_async.sync.aligned.m64n48k16.f32.bf16.bf16 {"
      "%0, %1, %2, %3, %4, %5, %6, %7, %8, %9, %10, %11, %12, %13, %14, %15, "
      "%16, %17, %18, %19, %20, %21, %22, %23"
      "}, da, db, p, 1, 1, 0, 1;\n}\n"
      : "+f"(d[0]), "+f"(d[1]), "+f"(d[2]), "+f"(d[3]), "+f"(d[4]), "+f"(d[5]), "+f"(d[6]), "+f"(d[7]),
        "+f"(d[8]), "+f"(d[9]), "+f"(d[10]), "+f"(d[11]), "+f"(d[12]), "+f"(d[13]), "+f"(d[14]), "+f"(d[15]),
        "+f"(d[16]), "+f"(d[17]), "+f"(d[18]), "+f"(d[19]), "+f"(d[20]), "+f"(d[21]), "+f"(d[22]), "+f"(d[23])
      : "r"(da), "n"(HA), "r"(db), "n"(HB), "r"(sc));
  }
};
template <> struct WgSST<80> {
  template <uint32_t HA, uint32_t HB>
  static __device__ __forceinline__ void mma(float* d, uint32_t da, uint32_t db, int sc) {
    asm volatile("{\n.reg .pred p;\n.reg .b64 da, db;\nsetp.ne.b32 p, %44, 0;\n"
      "mov.b64 da, {%40, %41};\nmov.b64 db, {%42, %43};\n"
      "wgmma.mma_async.sync.aligned.m64n80k16.f32.bf16.bf16 {"
      "%0, %1, %2, %3, %4, %5, %6, %7, %8, %9, %10, %11, %12, %13, %14, %15, "
      "%16, %17, %18, %19, %20, %21, %22, %23, %24, %25, %26, %27, %28, %29, %30, %31, "
      "%32, %33, %34, %35, %36, %37, %38, %39"
      "}, da, db, p, 1, 1, 0, 1;\n}\n"
      : "+f"(d[0]), "+f"(d[1]), "+f"(d[2]), "+f"(d[3]), "+f"(d[4]), "+f"(d[5]), "+f"(d[6]), "+f"(d[7]),
        "+f"(d[8]), "+f"(d[9]), "+f"(d[10]), "+f"(d[11]), "+f"(d[12]), "+f"(d[13]), "+f"(d[14]), "+f"(d[15]),
        "+f"(d[16]), "+f"(d[17]), "+f"(d[18]), "+f"(d[19]), "+f"(d[20]), "+f"(d[21]), "+f"(d[22]), "+f"(d[23]),
        "+f"(d[24]), "+f"(d[25]), "+f"(d[26]), "+f"(d[27]), "+f"(d[28]), "+f"(d[29]), "+f"(d[30]), "+f"(d[31]),
        "+f"(d[32]), "+f"(d[33]), "+f"(d[34]), "+f"(d[35]), "+f"(d[36]), "+f"(d[37]), "+f"(d[38]), "+f"(d[39])
      : "r"(da), "n"(HA), "r"(db), "n"(HB), "r"(sc));
  }
};
template <> struct WgSST<192> {
  template <uint32_t HA, uint32_t HB>
  static __device__ __forceinline__ void mma(float* d, uint32_t da, uint32_t db, int sc) {
    asm volatile("{\n.reg .pred p;\n.reg .b64 da, db;\nsetp.ne.b32 p, %100, 0;\n"
      "mov.b64 da, {%96, %97};\nmov.b64 db, {%98, %99};\n"
      "wgmma.mma_async.sync.aligned.m64n192k16.f32.bf16.bf16 {"
      "%0, %1, %2, %3, %4, %5, %6, %7, %8, %9, %10, %11, %12, %13, %14, %15, "
      "%16, %17, %18, %19, %20, %21, %22, %23, %24, %25, %26, %27, %28, %29, %30, %31, "
      "%32, %33, %34, %35, %36, %37, %38, %39, %40, %41, %42, %43, %44, %45, %46, %47, "
      "%48, %49, %50, %51, %52, %53, %54, %55, %56, %57, %58, %59, %60, %61, %62, %63, "
      "%64, %65, %66, %67, %68, %69, %70, %71, %72, %73, %74, %75, %76, %77, %78, %79, "
      "%80, %81, %82, %83, %84, %85, %86, %87, %88, %89, %90, %91, %92, %93, %94, %95"
      "}, da, db, p, 1, 1, 0, 1;\n}\n"
      : "+f"(d[0]), "+f"(d[1]), "+f"(d[2]), "+f"(d[3]), "+f"(d[4]), "+f"(d[5]), "+f"(d[6]), "+f"(d[7]),
        "+f"(d[8]), "+f"(d[9]), "+f"(d[10]), "+f"(d[11]), "+f"(d[12]), "+f"(d[13]), "+f"(d[14]), "+f"(d[15]),
        "+f"(d[16]), "+f"(d[17]), "+f"(d[18]), "+f"(d[19]), "+f"(d[20]), "+f"(d[21]), "+f"(d[22]), "+f"(d[23]),
        "+f"(d[24]), "+f"(d[25]), "+f"(d[26]), "+f"(d[27]), "+f"(d[28]), "+f"(d[29]), "+f"(d[30]), "+f"(d[31]),
        "+f"(d[32]), "+f"(d[33]), "+f"(d[34]), "+f"(d[35]), "+f"(d[36]), "+f"(d[37]), "+f"(d[38]), "+f"(d[39]),
        "+f"(d[40]), "+f"(d[41]), "+f"(d[42]), "+f"(d[43]), "+f"(d[44]), "+f"(d[45]), "+f"(d[46]), "+f"(d[47]),
        "+f"(d[48]), "+f"(d[49]), "+f"(d[50]), "+f"(d[51]), "+f"(d[52]), "+f"(d[53]), "+f"(d[54]), "+f"(d[55]),
        "+f"(d[56]), "+f"(d[57]), "+f"(d[58]), "+f"(d[59]), "+f"(d[60]), "+f"(d[61]), "+f"(d[62]), "+f"(d[63]),
        "+f"(d[64]), "+f"(d[65]), "+f"(d[66]), "+f"(d[67]), "+f"(d[68]), "+f"(d[69]), "+f"(d[70]), "+f"(d[71]),
        "+f"(d[72]), "+f"(d[73]), "+f"(d[74]), "+f"(d[75]), "+f"(d[76]), "+f"(d[77]), "+f"(d[78]), "+f"(d[79]),
        "+f"(d[80]), "+f"(d[81]), "+f"(d[82]), "+f"(d[83]), "+f"(d[84]), "+f"(d[85]), "+f"(d[86]), "+f"(d[87]),
        "+f"(d[88]), "+f"(d[89]), "+f"(d[90]), "+f"(d[91]), "+f"(d[92]), "+f"(d[93]), "+f"(d[94]), "+f"(d[95])
      : "r"(da), "n"(HA), "r"(db), "n"(HB), "r"(sc));
  }
};

struct FftConst {
  uint32_t f[2][4], fi[4][4];
  float ta[4], tb[4];
};
__device__ __forceinline__ void cis(int m, float scale, float& c, float& s) {
  const float a = (float)m * (-6.283185307179586f * scale);
  c = __cosf(a);
  s = __sinf(a);
}
__device__ __forceinline__ void fft_tables(uint32_t (&v)[12], int tw) {
  const int row = tw >> 2, ch = tw & 3;
#pragma unroll
  for (int i = 0; i < 4; i++) {
    float c[2], s[2], x[2];
#pragma unroll
    for (int e = 0; e < 2; e++) {
      cis((((32 * (8 * ch + 2 * i + e) + 15) * (4 * row - 63) + 2048) & 4095) - 2048, 1.f / 4096, c[e], s[e]);
      float gc, gs;
      cis((((row & 15) * (8 * (ch & 1) + 2 * i + e) + 8) & 15) - 8, 1.f / 16, gc, gs);
      x[e] = (row >> 4) == (ch >> 1) ? gc : (ch >> 1) ? gs : -gs;
    }
    v[i] = pack2(c[0] * 0.125f, c[1] * 0.125f);
    v[4 + i] = pack2(s[0] * 0.125f, s[1] * 0.125f);
    v[8 + i] = pack2(x[0], x[1]);
  }
#pragma unroll
  for (int i = 0; i < 12; i++) asm volatile("" : "+r"(v[i]));
}
__device__ __forceinline__ void fft_tables_store(const uint32_t (&v)[12], uint32_t sb, int tw) {
  const int row = tw >> 2;
  const uint32_t x = ((tw ^ (row >> 1)) & 3) << 4, a = sb + OFF_FT + (16 * (row >> 3) + (row & 7)) * 64 + x;
  sts128(a, v[0], v[1], v[2], v[3]);
  sts128(a + 512, v[4], v[5], v[6], v[7]);
  sts128(sb + OFF_GT + row * 64 + x, v[8], v[9], v[10], v[11]);
}
__device__ __forceinline__ void fft_twiddles(FftConst& k, int w, int lane) {
#pragma unroll
  for (int i = 0; i < 4; i++) {
    float c, s;
    cis((2 * (8 * (i >> 1) + 2 * (lane & 3) + (i & 1)) - 15) * (4 * (8 * w + (lane >> 2)) - 63), 1.f / 4096, c, s);
    k.ta[i] = __fdividef(-s, 1.f + c);
    k.tb[i] = s;
  }
  pin<4>(k.ta);
  pin<4>(k.tb);
}
__device__ __forceinline__ void fft_matrices(FftConst& k, uint32_t sb, int w, int lane) {
  const uint32_t x = (lane >> 1) & 3;
#pragma unroll
  for (int i = 0; i < 2; i++) {
    ldsm4(k.f[i], sb + OFF_FT + (16 * w + (lane & 15)) * 64 + (((2 * i + (lane >> 4)) ^ x) << 4));
    ldsm4t(k.fi[i], sb + OFF_FT + (32 * i + lane) * 64 + ((w ^ x) << 4));
#pragma unroll
    for (int j = 0; j < 4; j++) {
      k.fi[2 + i][j] = (j & 1) ? k.fi[i][j - 1] ^ 0x80008000u : k.fi[i][j + 1];
      asm volatile("" : "+r"(k.fi[2 + i][j]));
    }
  }
}
template <bool INV> __device__ __forceinline__ void rot(float& x, float& y, float a, float b) {
  x = fmaf(INV ? -a : a, y, x);
  y = fmaf(INV ? -b : b, x, y);
  x = fmaf(INV ? -a : a, y, x);
}
__device__ __forceinline__ void twiddle_fwd(uint32_t (&a)[4][4], float* d, const FftConst& k) {
#pragma unroll
  for (int q = 0; q < 4; q++)
#pragma unroll
    for (int j = 0; j < 2; j++) {
      float* x = d + 8 * q + 4 * j;
      rot<false>(x[0], x[2], k.ta[2 * j], k.tb[2 * j]);
      rot<false>(x[1], x[3], k.ta[2 * j + 1], k.tb[2 * j + 1]);
      a[q & 2][2 * j + (q & 1)] = pack2(x[0], x[1]);
      a[(q & 2) + 1][2 * j + (q & 1)] = pack2(x[2], x[3]);
    }
}
__device__ __forceinline__ void g_step(float* d, const uint32_t (&a)[4][4], uint32_t dre, uint32_t dim) {
  WgRS<32>::set<HI_SW64>(d, a[0], dre);
  WgRS<32>::set<HI_SW64>(d + 16, a[2], dre);
  WgRS<32>::mma<HI_SW64>(d, a[1], dim);
  WgRS<32>::mma<HI_SW64>(d + 16, a[3], dim);
  wg_commit();
}

__device__ __forceinline__ void conv_channel(const FftConst& k, uint32_t sb, int c, int wg, int w, int lane) {
  const uint32_t cb = sb + off_ch(c), bars = sb + OFF_BAR;
  const uint32_t du = desc_lo(cb, 1024), dg = desc_lo(sb + OFF_GT, 16), dz = desc_lo(cb + U_BYTES, 16);
  float U[32], H[32];
  uint32_t a[4][4], e[4][4];
  const float dv = __uint_as_float(lds32(sb + OFF_D + 4 * c));
  wg_fence();
  WgRS<64>::set<HI_SW32>(H, k.f[0], du + 256);
  WgRS<64>::mma<HI_SW32>(H, k.f[1], du + 256 + 32);
  wg_commit();
  wg_wait<0>();
  pin<32>(H);
  twiddle_fwd(a, H, k);
  if (ATT_GATE && H_EARLY) mbar_wait(bars + 8 * B_ATTN, 0);
  mbar_wait(bars + 8 * (B_U + (c < 3 ? c : 3)), 0);
  TSM(w == 0 && c < 3, 7 + wg);
  if (TOK_G < 8 && c > 0) mbar_wait(bars + 8 * (B_TOK + c - 1), 0);
  wg_fence();
  WgRS<64>::set<HI_SW32>(U, k.f[0], du);
  WgRS<64>::mma<HI_SW32>(U, k.f[1], du + 32);
  wg_commit();
  g_step(H, a, dg, dg + 64);
  wg_wait<1>();
  pin<32>(U);
  if (TOK_G == 1 && lane == 0) mbar_arrive(bars + 8 * (B_TOK + c));
  twiddle_fwd(e, U, k);
  wg_fence();
  g_step(U, e, dg, dg + 64);
  if (TOK_G == 2 && lane == 0) mbar_arrive(bars + 8 * (B_TOK + c));
  wg_wait<0>();
  pin<32>(U);
  pin<32>(H);
#pragma unroll
  for (int j = 0; j < 2; j++) {
    float pr[4][2], pi[4][2];
#pragma unroll
    for (int x = 0; x < 2; x++) {
      H[4 * j + x] += dv;
#pragma unroll
      for (int m = 0; m < 4; m++) {
#pragma unroll
        for (int q = 0; q <= m; q++) {
          const int ih = 16 * (q >> 1) + 2 * (q & 1) + 4 * j + x, iu = 16 * ((m - q) >> 1) + 2 * ((m - q) & 1) + 4 * j + x;
          pr[m][x] = q ? fmaf(H[ih], U[iu], pr[m][x]) : H[ih] * U[iu];
          pi[m][x] = q ? fmaf(H[ih], U[iu + 8], pi[m][x]) : H[ih] * U[iu + 8];
          pr[m][x] = fmaf(-H[ih + 8], U[iu + 8], pr[m][x]);
          pi[m][x] = fmaf(H[ih + 8], U[iu], pi[m][x]);
        }
      }
    }
#pragma unroll
    for (int m = 0; m < 4; m++) {
      a[m & 2][2 * j + (m & 1)] = pack2(pr[m][0], pr[m][1]);
      a[(m & 2) + 1][2 * j + (m & 1)] = pack2(pi[m][0], pi[m][1]);
    }
  }
  wg_fence();
  g_step(U, a, dg + 64, dg);
  if (TOK_G == 3 && lane == 0) mbar_arrive(bars + 8 * (B_TOK + c));
  const uint32_t za = cb + U_BYTES + (8 * w + (lane & 7)) * 128 + (((lane >> 3) ^ (lane & 7)) << 4);
  const uint32_t ya = cb + (lane >> 4) * 1024 + (8 * w + (lane & 7)) * 32 + ((((lane >> 3) ^ (lane >> 2)) & 1) << 4);
  wg_sync(1 + wg);
  wg_wait<0>();
  pin<32>(U);
  TSIF(w == 0, 80 + c);
#pragma unroll
  for (int p = 0; p < 2; p++) {
#pragma unroll
    for (int i = 0; i < 4; i++) {
      const int j = i & 1;
      float* x = U + 16 * p + 4 * j + (i & 2);
      rot<true>(x[8], x[0], k.ta[2 * j], k.tb[2 * j]);
      rot<true>(x[9], x[1], k.ta[2 * j + 1], k.tb[2 * j + 1]);
      e[p][i] = pack2(x[8], x[9]);
      e[2 + p][i] = pack2(x[0], x[1]);
    }
    stsm4(za ^ (64 * p), e[p]);
    stsm4((za ^ (64 * p)) + 4096, e[2 + p]);
  }
  fence_async_smem();
  wg_sync(1 + wg);
  wg_fence();
  WgRS<64>::set<HI_SW128>(H, k.fi[0], dz);
#pragma unroll
  for (int ks = 1; ks < 4; ks++) WgRS<64>::mma<HI_SW128>(H, k.fi[ks], dz + 128 * ks);
  wg_commit();
  wg_wait<0>();
  pin<32>(H);
  TSIF(w == 0, 88 + c);
#pragma unroll
  for (int j = 0; j < 8; j++)
    a[j >> 2][j & 3] = j < 2 ? pack2(H[4 * j], H[4 * j + 1]) : pack2(H[4 * j] + H[4 * j - 6], H[4 * j + 1] + H[4 * j - 5]);
  stsm4(ya, a[0]);
  stsm4(ya + 2048, a[1]);
  fence_async_smem();
  __syncwarp();
}

__device__ __forceinline__ void prep_slab(uint4* res, const uint2* sw, uint32_t sb, int slab, int w, int lane) {
  const int t = lane & 3, tp = (lane & 7) >> 1, pos = 8 * tp + 2 * (((lane >> 3) + tp) & 3) + (lane & 1);
  const uint32_t base = sb + OFF_KVS + slab * KVS_BYTES + pos * 128;
  uint32_t kk[2][4][4], vv[2][4];
  mbar_wait(sb + OFF_BAR + 8 * (B_KV + slab), 0);
#pragma unroll
  for (int h = 0; h < 2; h++) {
#pragma unroll
    for (int j = 0; j < 4; j++) {
      const uint32_t a = base + 128 * j;
      ldsm4t(kk[h][j], a + (((w + 4 * h) ^ ((a >> 7) & 7)) << 4));
    }
    const uint32_t a = base + KVS_V;
    ldsm4t(vv[h], a + (((w + 4 * h) ^ ((a >> 7) & 7)) << 4));
  }
#pragma unroll
  for (int h = 0; h < 2; h++) {
    uint32_t (&k)[4][4] = kk[h];
    uint32_t (&v)[4] = vv[h];
    const uint32_t w0 = __byte_perm(sw[h].x, 0, 0x1010), w1 = __byte_perm(sw[h].x, 0, 0x3232);
    const uint32_t w2 = __byte_perm(sw[h].y, 0, 0x1010), w3 = __byte_perm(sw[h].y, 0, 0x3232);
#pragma unroll
    for (int m = 0; m < 4; m++)
      v[m] = bmul(badd(badd(badd(bmul(k[0][m], w3), bmul(k[1][m], w2)), bmul(k[2][m], w1)), bmul(k[3][m], w0)), v[m]);
    uint32_t a[4];
#pragma unroll
    for (int m = 0; m < 4; m++) a[m] = (t & 1) ? v[(m + 3) & 3] : v[m];
    res[h] = (t & 2) ? make_uint4(a[2], a[3], a[0], a[1]) : make_uint4(a[0], a[1], a[2], a[3]);
  }
}

__device__ __forceinline__ void prep_gate(const Params& p, int b, int w, int lane) {
  uint2 gw[5], x[4][5];
#pragma unroll
  for (int j = 0; j < 5; j++) gw[j] = ldg64(reinterpret_cast<const uint2*>(p.gate_w) + lane + 32 * j);
#pragma unroll
  for (int i = 0; i < 4; i++)
#pragma unroll
    for (int j = 0; j < 5; j++)
      x[i][j] = ldg64(reinterpret_cast<const uint2*>(p.q) + (16 * b + 4 * w + i) * (DIM / 4) + lane + 32 * j);
  float s[4];
#pragma unroll
  for (int i = 0; i < 4; i++) {
    s[i] = 0.f;
#pragma unroll
    for (int j = 0; j < 5; j++) {
      const uint32_t m0 = bmul(x[i][j].x, gw[j].x), m1 = bmul(x[i][j].y, gw[j].y);
      s[i] += (bf_lo(m0) + bf_hi(m0)) + (bf_lo(m1) + bf_hi(m1));
    }
  }
  const bool h = lane & 16, q = lane & 8;
  const float a = (h ? s[2] : s[0]) + __shfl_xor_sync(0xffffffffu, h ? s[0] : s[2], 16);
  const float c = (h ? s[3] : s[1]) + __shfl_xor_sync(0xffffffffu, h ? s[1] : s[3], 16);
  float z = (q ? c : a) + __shfl_xor_sync(0xffffffffu, q ? a : c, 8);
#pragma unroll
  for (int o = 4; o > 0; o >>= 1) z += __shfl_xor_sync(0xffffffffu, z, o);
  z = bf_lo(pack2(z, 0.f));
  if ((lane & 7) == 0) g_gate[16 * b + 4 * w + (lane >> 3)] = bf_lo(pack2(__fdividef(1.f, 1.f + __expf(-z)), 0.f));
}

__device__ __forceinline__ uint32_t bmax(uint32_t a, uint32_t b) {
  uint32_t d;
  asm("max.bf16x2 %0, %1, %2;" : "=r"(d) : "r"(a), "r"(b));
  return d;
}
__device__ __forceinline__ void softmax_two(const float (&l)[2][2], uint32_t& p0, uint32_t& p1) {
  constexpr float kScale = 0.22360679774997896f, kLog2e = 1.4426950408889634f;
  const uint32_t r0 = pack2(l[0][0], l[1][0]), r1 = pack2(l[0][1], l[1][1]);
  const uint32_t x0 = pack2(bf_lo(r0) * kScale, bf_hi(r0) * kScale), x1 = pack2(bf_lo(r1) * kScale, bf_hi(r1) * kScale);
  uint32_t m = bmax(x0, x1);
  m = bmax(m, __shfl_xor_sync(0xffffffffu, m, 1));
  m = bmax(m, __shfl_xor_sync(0xffffffffu, m, 2));
  const float m0 = bf_lo(m) * kLog2e, m1 = bf_hi(m) * kLog2e;
  p0 = pack2(ex2(bf_lo(x0) * kLog2e - m0), ex2(bf_lo(x1) * kLog2e - m0));
  p1 = pack2(ex2(bf_hi(x0) * kLog2e - m1), ex2(bf_hi(x1) * kLog2e - m1));
}

__device__ __forceinline__ void halo_read(uint32_t (&kpv)[10], uint32_t (&vpv)[10], uint32_t (&tg)[7], const uint4* hp) {
#pragma unroll
  for (int j = 0; j < 7; j++) {
    uint32_t x0, x1, x2;
    asm volatile("ld.relaxed.gpu.global.v4.u32 {%0, %1, %2, %3}, [%4];"
                 : "=r"(x0), "=r"(x1), "=r"(x2), "=r"(tg[j]) : "l"(hp + 32 * j) : "memory");
    if (j < 4) kpv[3 * j] = x0; else vpv[3 * j - 10] = x0;
    if (j < 3) kpv[3 * j + 1] = x1; else vpv[3 * j - 9] = x1;
    if (j < 3) kpv[3 * j + 2] = x2; else if (j < 6) vpv[3 * j - 8] = x2;
  }
}

template <int ROT>
__device__ __forceinline__ void pack_qkv(const float* acc, uint32_t (&qlo)[10], uint32_t (&qhi)[10], uint32_t (&klo)[10],
                                         uint32_t (&khi)[10], uint32_t (&vlo)[10], uint32_t (&vhi)[10]) {
#pragma unroll
  for (int j = 0; j < 10; j++) {
    const int x = (j + ROT) % 10, tq = x < 8 ? x : 16 + x, tk = x < 8 ? 8 + x : 18 + x, tv = x < 8 ? 16 + x : 20 + x;
    khi[j] = pack2(acc[4 * tk + 2], acc[4 * tk + 3]);
    vhi[j] = movm(pack2(acc[4 * tv + 2], acc[4 * tv + 3]));
    qlo[j] = pack2(acc[4 * tq], acc[4 * tq + 1]);
    qhi[j] = pack2(acc[4 * tq + 2], acc[4 * tq + 3]);
    klo[j] = pack2(acc[4 * tk], acc[4 * tk + 1]);
    vlo[j] = pack2(acc[4 * tv], acc[4 * tv + 1]);
    asm volatile("" : "+r"(khi[j]), "+r"(qlo[j]), "+r"(qhi[j]), "+r"(klo[j]), "+r"(vlo[j]));
  }
}

__device__ __forceinline__ void attention(float* acc, uint32_t sb, int b, int par, int w, int lane) {
  const int g = lane >> 2, t = lane & 3;
  uint32_t klo[10], khi[10], vlo[10], vhi[10], qlo[10], qhi[10], kpv[10], vpv[10];
  if (tail_first(b & 7)) pack_qkv<8>(acc, qlo, qhi, klo, khi, vlo, vhi);
  else pack_qkv<0>(acc, qlo, qhi, klo, khi, vlo, vhi);
  uint32_t tag = 0;
  if (w == 0 || w == 3) {
    mbar_wait(sb + OFF_BAR + 8 * B_EPOCH, 0);
    tag = lds32(sb + OFF_EPOCH) + 1;
  }
  const uint32_t xa = sb + OFF_KVX + (par * 3) * 2560 + lane * 16;
  if (w < 3) {
    mbar_wait(sb + OFF_BAR + 8 * B_S3, 0);
    sts128(xa + w * 2560, khi[0], khi[1], khi[2], khi[3]);
    sts128(xa + w * 2560 + 512, khi[4], khi[5], khi[6], khi[7]);
    sts128(xa + w * 2560 + 1024, khi[8], khi[9], vhi[0], vhi[1]);
    sts128(xa + w * 2560 + 1536, vhi[2], vhi[3], vhi[4], vhi[5]);
    sts128(xa + w * 2560 + 2048, vhi[6], vhi[7], vhi[8], vhi[9]);
  } else if (b < NCTA - 8) {
    uint4* ho = g_halo + (b * 2 + par) * 224 + lane;
#pragma unroll
    for (int j = 0; j < 7; j++) {
      const uint32_t x0 = j < 4 ? khi[3 * j] : vhi[3 * j - 10], x1 = j < 3 ? khi[3 * j + 1] : vhi[3 * j - 9];
      const uint32_t x2 = j < 3 ? khi[3 * j + 2] : j < 6 ? vhi[3 * j - 8] : 0u;
      asm volatile("st.relaxed.gpu.global.v4.u32 [%0], {%1, %2, %3, %4};" ::"l"(ho + 32 * j), "r"(x0), "r"(x1), "r"(x2), "r"(tag) : "memory");
    }
  }
  TSIF(par == 0 && w == 1, 64);
  TSIF(par == 0 && w == 3, 76);
#pragma unroll
  for (int j = 0; j < 10; j++) vlo[j] = movm(vlo[j]);
  const bool far0 = 2 * t > g, far1 = 2 * t + 1 > g;
  const uint32_t mfar = (far0 ? 0x0000FFFFu : 0u) | (far1 ? 0xFFFF0000u : 0u);
  float slo[4][2], shi[4][2], lg[2][2];
  uint32_t phi[4], plo[4], qml[4], qmh[4];
#pragma unroll
  for (int h = 0; h < 4; h++) {
    const int f = h == 0 ? 0 : h == 1 ? 3 : h == 2 ? 5 : 8, hf = h < 2 ? 2 : 7;
    const bool mine = (h & 1) ? t >= 2 : t < 2;
    qml[h] = mine ? qlo[hf] : 0u;
    qmh[h] = mine ? qhi[hf] : 0u;
    float a[4] = {0.f, 0.f, 0.f, 0.f}, c[4] = {0.f, 0.f, 0.f, 0.f};
    mma16816(a, qlo[f], qhi[f], qlo[f + 1], qhi[f + 1], klo[f], klo[f + 1]);
    mma16816(c, qlo[f], qhi[f], qlo[f + 1], qhi[f + 1], khi[f], khi[f + 1]);
    mma1688(a, qml[h], qmh[h], klo[hf]);
    mma1688(c, qml[h], qmh[h], khi[hf]);
    slo[h][0] = a[0];
    slo[h][1] = a[1];
    shi[h][0] = lg[h & 1][0] = far0 ? a[2] : c[2];
    shi[h][1] = lg[h & 1][1] = far1 ? a[3] : c[3];
    if (!ATT_MERGE && (h & 1)) softmax_two(lg, phi[h - 1], phi[h]);
  }
  TSIF(par == 0 && w == 1, 65);
  wg_sync(1 + par);
  TSIF(par == 0 && w == 1, 66);
  const bool nohist = (w == 0) && (b < 8);
  const uint4* hp = g_halo + ((b - 8) * 2 + par) * 224 + lane;
  uint32_t tg[7];
  if (w > 0) {
    const uint4 v0 = lds128(xa + (w - 1) * 2560), v1 = lds128(xa + (w - 1) * 2560 + 512), v2 = lds128(xa + (w - 1) * 2560 + 1024);
    const uint4 v3 = lds128(xa + (w - 1) * 2560 + 1536), v4 = lds128(xa + (w - 1) * 2560 + 2048);
    kpv[0] = v0.x; kpv[1] = v0.y; kpv[2] = v0.z; kpv[3] = v0.w; kpv[4] = v1.x; kpv[5] = v1.y; kpv[6] = v1.z; kpv[7] = v1.w;
    kpv[8] = v2.x; kpv[9] = v2.y; vpv[0] = v2.z; vpv[1] = v2.w; vpv[2] = v3.x; vpv[3] = v3.y; vpv[4] = v3.z; vpv[5] = v3.w;
    vpv[6] = v4.x; vpv[7] = v4.y; vpv[8] = v4.z; vpv[9] = v4.w;
  } else if (nohist) {
#pragma unroll
    for (int j = 0; j < 10; j++) kpv[j] = vpv[j] = 0u;
  } else {
    TSIF(par == 0, 77);
    halo_read(kpv, vpv, tg, hp);
  }
  if (w == 0 && !nohist) {
    int spins = 0;
    while (true) {
      bool ok = true;
#pragma unroll
      for (int j = 0; j < 7; j++) ok = ok && tg[j] == tag;
      if (__all_sync(0xffffffffu, ok) || ++spins > SPIN_LIMIT) break;
      halo_read(kpv, vpv, tg, hp);
    }
    TSIF(par == 0, 79);
  }
#pragma unroll
  for (int h = 0; h < 4; h++) {
    const int f = h == 0 ? 0 : h == 1 ? 3 : h == 2 ? 5 : 8, hf = h < 2 ? 2 : 7;
    float a[4] = {0.f, 0.f, 0.f, 0.f};
    mma16816(a, qlo[f], qhi[f], qlo[f + 1], qhi[f + 1], kpv[f], kpv[f + 1]);
    mma1688(a, qml[h], qmh[h], kpv[hf]);
    const float ninf = __int_as_float(0xff800000);
    lg[h & 1][0] = far0 ? (nohist ? ninf : a[0]) : slo[h][0];
    lg[h & 1][1] = far1 ? (nohist ? ninf : a[1]) : slo[h][1];
    if (h & 1) {
      softmax_two(lg, plo[h - 1], plo[h]);
      if (ATT_MERGE) {
        const float lh[2][2] = {{shi[h - 1][0], shi[h - 1][1]}, {shi[h][0], shi[h][1]}};
        softmax_two(lh, phi[h - 1], phi[h]);
      }
    }
  }
  TSIF(par == 0 && w <= 1, 67 + w);
  uint32_t ov[20];
#pragma unroll
  for (int hp = 0; hp < 2; hp++) {
    const int hf = hp ? 7 : 2;
    float sh[4] = {0.f, 0.f, 0.f, 0.f}, i0 = 0.f, i1 = 0.f;
#pragma unroll
    for (int e = 0; e < 2; e++) {
      const int h = 2 * hp + e, f = h == 0 ? 0 : h == 1 ? 3 : h == 2 ? 5 : 8;
      const uint32_t a0 = plo[h] & mfar, a2 = plo[h] & ~mfar, a3 = phi[h] & mfar, c1 = phi[h] & ~mfar;
      float sum[4] = {0.f, 0.f, 0.f, 0.f};
      mma1688(sum, plo[h], phi[h], 0x3F803F80u);
      const float r0 = rcp(sum[0]), r1 = rcp(sum[2]);
#pragma unroll
      for (int j = f; j < f + 2; j++) {
        float o[4] = {0.f, 0.f, 0.f, 0.f};
        mma16816(o, a0, 0u, a2, a3, vpv[j], vlo[j]);
        mma1688(o, 0u, c1, vhi[j]);
        ov[2 * j] = pack2(o[0] * r0, o[1] * r0);
        ov[2 * j + 1] = pack2(o[2] * r1, o[3] * r1);
      }
      const bool mine = e ? g >= 4 : g < 4;
      mma16816(sh, a0, 0u, a2, a3, mine ? vpv[hf] : 0u, mine ? vlo[hf] : 0u);
      mma1688(sh, 0u, c1, mine ? vhi[hf] : 0u);
      if (e == 0 || t >= 2) {
        i0 = r0;
        i1 = r1;
      }
    }
    ov[2 * hf] = pack2(sh[0] * i0, sh[1] * i0);
    ov[2 * hf + 1] = pack2(sh[2] * i1, sh[3] * i1);
  }
  TS(32 + 4 * par + w);
  mbar_wait(sb + OFF_BAR + 8 * B_P1, 0);
  const uint32_t oa = sb + OFF_OA + (lane >> 4) * 2048 + (32 * w + 2 * (lane & 15) + par) * 16;
#pragma unroll
  for (int j = 0; j < 5; j++) stsm4(oa + 4096 * j, ov + 4 * j);
  TSIF(par == 0 && w == 0, 120);
  fence_async_smem();
  TSIF(par == 0 && w == 0, 121);
  __syncwarp();
  if (lane == 0) mbar_arrive(sb + OFF_BAR + 8 * B_ATTN);
  TSIF(par == 0 && w == 0, 122);
}

struct Maps {
  CUtensorMap x, wm, wt, k, v, y, wo, qm, qt, om, ot;
};

__device__ __forceinline__ void load_stage(uint32_t sb, int kb, int b, const Maps& m) {
  const uint32_t st = sb + (kb & 3) * STAGE_BYTES, bar = sb + OFF_BAR + 8 * (B_FULL1 + (kb & 3));
  const int r = b >> 3, hg = b & 7, slab = kb - KV_KB;
  const bool kv = slab >= 0 && slab < 5;
  const uint32_t kbar = sb + OFF_BAR + 8 * (B_KV + slab), dst = sb + OFF_KVS + slab * KVS_BYTES;
  mbar_expect_tx(bar, STAGE_BYTES);
  if (kv) mbar_expect_tx(kbar, KVS_BYTES);
  tma_3d(st, &m.x, 64 * kb, 64 * r, 0, bar);
  if (kv && KV_MIX) tma_3d(dst, &m.k, 0, 32 * (b >> 1) - 3, 2 * slab + (b & 1), kbar);
  tma_3d(st + ST_W, &m.wm, 80 * hg + (tail_first(hg) ? 16 : 0), 64 * kb, 0, bar);
  if (kv && KV_MIX) tma_3d(dst + KVS_V, &m.v, 0, 32 * (b >> 1), 2 * slab + (b & 1), kbar);
  tma_3d(st + ST_WT, &m.wt, 80 * hg + (tail_first(hg) ? 0 : 64), 64 * kb, 0, bar);
  if (kv && !KV_MIX) tma_3d(dst, &m.k, 0, 32 * (b >> 1) - 3, 2 * slab + (b & 1), kbar);
  if (kv && !KV_MIX) tma_3d(dst + KVS_V, &m.v, 0, 32 * (b >> 1), 2 * slab + (b & 1), kbar);
}

__global__ void __launch_bounds__(NTHR, 1) fused_kernel(const __grid_constant__ Maps m, const Params p) {
  extern __shared__ __align__(1024) uint8_t smem[];
  const uint32_t sb = (uint32_t)__cvta_generic_to_shared(smem);
  const uint32_t bars = sb + OFF_BAR;
  const int tid = threadIdx.x, lane = tid & 31;
  int b = blockIdx.x;
  if (BMAP == 1) b = (((b & 63) >> 3) * 2 + (b & 1)) * 8 + (((b < 64 ? 0x6521 : 0x7430) >> (4 * ((b >> 1) & 3))) & 7);
  if (BMAP == 2) b = ((b & 63) >> 2) * 8 + (((b < 64 ? 0x6521 : 0x7430) >> (4 * (b & 3))) & 7);
  if (BMAP == 3) b = (((b & 63) >> 3) * 2 + (b & 1)) * 8 + (((b < 64 ? 0x7430 : 0x6521) >> (4 * ((b >> 1) & 3))) & 7);
  if (BMAP == 4) b = (((b >> 4) * 2 + (b & 1)) * 8) + ((b >> 1) & 7);
  if (BMAP == 5) b = 127 - b;
  const int r = b >> 3, hg = b & 7;

  if (tid == T_ISSUE) {
    TSM(true, 0);
#pragma unroll
    for (int i = 0; i < 4; i++) mbar_init(bars + 8 * (B_FULL1 + i), 1);
#pragma unroll
    for (int i = 0; i < 3; i++) mbar_init(bars + 8 * (B_KV + i), 1);
    fence_async_smem();
#pragma unroll 1
    for (int kb = 0; kb <= PRE2; kb++) load_stage(sb, kb, b, m);
  } else if (tid >= T_PF && tid < T_PF + 11) {
    tm_prefetch(&m.x + (tid - T_PF));
  } else if (tid == T_INIT) {
#pragma unroll
    for (int i = 0; i < 4; i++) mbar_init(bars + 8 * (B_EMPTY1 + i), 8);
#pragma unroll
    for (int i = 0; i < 8; i++) mbar_init(bars + 8 * (B_FULL2 + i), 1);
#pragma unroll
    for (int i = 0; i < 4; i++) mbar_init(bars + 8 * (B_EMPTY2 + i), 8);
#pragma unroll
    for (int i = 0; i < 4; i++) mbar_init(bars + 8 * (B_U + i), 1);
    mbar_init(bars + 8 * B_HA, 4);
    mbar_init(bars + 8 * B_GATE, 4);
    mbar_init(bars + 8 * B_HB, 1);
    mbar_init(bars + 8 * B_KVD, 4);
    mbar_init(bars + 8 * B_QF, 1);
    mbar_init(bars + 8 * B_ATTN, 8);
    mbar_init(bars + 8 * B_P1, 8);
    mbar_init(bars + 8 * B_C34, 1);
#pragma unroll
    for (int i = 0; i < 5; i++) mbar_init(bars + 8 * (B_YST + i), 4);
#pragma unroll
    for (int i = 0; i < 5; i++) mbar_init(bars + 8 * (B_TOK + i), 4);
    mbar_init(bars + 8 * B_YSIG, 1);
    mbar_init(bars + 8 * B_YFULL, 1);
    mbar_init(bars + 8 * B_EPOCH, 1);
    mbar_init(bars + 8 * B_PREP, 4);
    mbar_init(bars + 8 * B_USIG, 1);
    mbar_init(bars + 8 * B_WST, 1);
#pragma unroll
    for (int i = 3; i < 5; i++) mbar_init(bars + 8 * (B_KV + i), 1);
    mbar_init(bars + 8 * B_E3, 8);
    mbar_init(bars + 8 * B_LAST, 1);
    mbar_init(bars + 8 * B_OSIG, 1);
    mbar_init(bars + 8 * B_WOP, 1);
    fence_async_smem();
  }
  const int warp = __shfl_sync(0xffffffffu, tid >> 5, 0), wg = warp >> 2, w = warp & 3;
  __syncthreads();

  if (wg == 3) {
    asm volatile("setmaxnreg.dec.sync.aligned.u32 56;");
    if (w == 0) {
      if (lane == 0) {
#pragma unroll 1
        for (int kb = 1 + PRE2; kb < 10; kb++) {
          if (kb >= 4) mbar_wait(bars + 8 * (kb == 7 ? B_E3 : B_EMPTY1 + (kb & 3)), (kb >> 3) & 1);
          TSIF(kb >= 4, 44 + kb);
          load_stage(sb, kb, b, m);
          if (kb == TRIG_KB) mbar_arrive(bars + 8 * B_LAST);
        }
        mbar_wait(bars + 8 * B_WOP, 0);
        mbar_wait(bars + 8 * B_P1, 0);
        mbar_wait(bars + 8 * WL_TRIG, 0);
        mbar_wait(bars + 8 * B_EPOCH, 0);
        flag_wait(g_cnt + C_W + 32 * hg, (lds32(sb + OFF_EPOCH) + 1) * 16);
        TS(30);
#pragma unroll 1
        for (int j = 0; j < 8; j++) {
          if (j >= 6) mbar_wait(bars + 8 * (B_EMPTY2 + j - 6), 0);
          if (j == 4) mbar_wait(bars + 8 * B_ATTN, 0);
          TSIF(j >= 6, 100 + j);
          if (RF_GATE && j == 6) mbar_wait(bars + 8 * B_YSIG, 0);
          mbar_expect_tx(bars + 8 * (B_FULL2 + j), j == 0 ? WO_BYTES : j == 5 ? O_BYTES + WO_BYTES + 512 : O_BYTES + WO_BYTES);
          bulk_load(sb + off_w(j), g_WO + (hg * 8 + step_src(hg, j)) * 800, WO_BYTES, bars + 8 * (B_FULL2 + j));
        }
        mbar_wait(bars + 8 * (B_EMPTY2 + 3), 0);
        mbar_expect_tx(bars + 8 * B_QF, O_BYTES);
        tma_2d(sb + OFF_QS, &m.qm, 80 * hg, 128 * r, bars + 8 * B_QF);
        tma_2d(sb + OFF_QT, &m.qt, 80 * hg + 64, 128 * r, bars + 8 * B_QF);
      }
    } else if (w == 1) {
      unsigned epoch = 0;
      if (lane == 0) {
        epoch = atomicAdd(g_cnt + C_LAUNCH, 1u) / NCTA;
        asm volatile("st.shared.u32 [%0], %1;" ::"r"(sb + OFF_EPOCH), "r"(epoch) : "memory");
        mbar_arrive(bars + 8 * B_EPOCH);
        mbar_wait(bars + 8 * B_KVD, 0);
        mbar_expect_tx(bars + 8 * B_HB, 5 * 4096);
#pragma unroll 1
        for (int c = 0; c < 5; c++) {
          if (c == 3) mbar_wait(bars + 8 * B_S3, 0);
          bulk_load(sb + off_ch(c) + U_BYTES, p.ssm_k + (5 * b + c) * SEQ, 4096, bars + 8 * B_HB);
        }
#pragma unroll
        for (int c = 0; c < 4; c++) mbar_expect_tx(bars + 8 * (B_U + c), c < 3 ? U_BYTES : 2 * U_BYTES);
        const uint4* usrc = g_U + 5 * b * U_PITCH;
        mbar_wait(bars + 8 * B_USIG, 0);
        flag_wait(g_cnt + C_PREP + 32 * (b & 15), (epoch + 1) * NCTA);
        TS(23);
#pragma unroll
        for (int c = 0; c < 5; c++) {
          if (c == 3) mbar_wait(bars + 8 * (B_U + 2), 0);
          bulk_load(sb + off_ch(c), usrc + c * U_PITCH, U_BYTES, bars + 8 * (B_U + (c < 3 ? c : 3)));
          TSIF(c == 0 || c == 4, 116 + (c >> 2));
        }
      }
      epoch = __shfl_sync(0xffffffffu, epoch, 0);
      if (lane < 8) {
        const int src = (b & ~7) | step_src(hg, lane);
        mbar_wait(bars + 8 * B_OSIG, 0);
        TS(20);
        flag_wait(g_cnt + C_O + 32 * src, epoch + 1);
        if (lane >= 1 && lane < 4) bulk_load(sb + off_o(lane), g_O + src * 1280, O_BYTES, bars + 8 * (B_FULL2 + lane));
        __syncwarp(0xff);
        TS(21);
        if (lane == 5) bulk_load(sb + OFF_GATE, g_gate + 128 * r, 512, bars + 8 * (B_FULL2 + 5));
#pragma unroll 1
        for (int j = 4; j < 8; j++) {
          if (lane == j) {
            mbar_wait(bars + 8 * (j < 6 ? B_C34 : B_EMPTY2 + j - 6), 0);
            if (RF_GATE && j == 6) mbar_wait(bars + 8 * B_YSIG, 0);
            bulk_load(sb + off_o(j), g_O + src * 1280, O_BYTES, bars + 8 * (B_FULL2 + j));
          }
          __syncwarp(0xff);
        }
        TS(22);
      }
    } else if (w == 2) {
      mbar_wait(bars + 8 * B_PREP, 0);
      flag_signal(g_cnt + C_PREP, 16, lane);
      TS(25);
      if (lane == 0) mbar_arrive(bars + 8 * B_USIG);
      mbar_wait(bars + 8 * B_GATE, 0);
      if ((NOMB & 1) && lane == 0) asm volatile("fence.release.gpu;" ::: "memory");
      mbar_wait(bars + 8 * B_ATTN, 0);
      if (lane == 0) {
        if (O_DEFER) mbar_wait(bars + 8 * (B_U + 3), 0);
        asm volatile("cp.async.bulk.global.shared::cta.bulk_group [%0], [%1], 20480;\ncp.async.bulk.commit_group;\n"
                     "cp.async.bulk.wait_group 0;\nfence.proxy.async.global;" ::"l"(g_O + b * 1280), "r"(sb + OFF_OA) : "memory");
      }
      TS(74);
      if (!(NOMB & 1)) flag_signal(g_cnt + C_O + 32 * b, 1, lane);
      else if (lane == 0) flag_bump(g_cnt + C_O + 32 * b);
      TS(26);
      if (lane == 0) mbar_arrive(bars + 8 * B_OSIG);

    } else {
      if (lane == 0) {
        uint4* dst = g_WO + (hg * 8 + (r >> 1)) * 800 + (r & 1) * 80;
        mbar_wait(bars + 8 * B_P1, 0);
        mbar_wait(bars + 8 * WB_TRIG, 0);
        mbar_expect_tx(bars + 8 * B_WST, WO_BYTES / 2);
        tma_3d(sb + OFF_WS, &m.wo, 0, 40 * r, 5 * hg, bars + 8 * B_WST);
        mbar_wait(bars + 8 * B_WST, 0);
        mbar_wait(bars + 8 * WO_TRIG, 0);
#pragma unroll 1
        for (int n = 0; n < 5; n++)
          asm volatile("cp.async.bulk.global.shared::cta.bulk_group [%0], [%1], 1280;" ::"l"(dst + 160 * n), "r"(sb + OFF_WS + 1280 * n) : "memory");
        asm volatile("cp.async.bulk.commit_group;\ncp.async.bulk.wait_group 0;\nfence.proxy.async.global;" ::: "memory");
        if (!(NOMB & 4)) asm volatile("fence.release.gpu;" ::: "memory");
        flag_bump(g_cnt + C_W + 32 * hg);
        mbar_arrive(bars + 8 * B_WOP);
        TS(71);
#pragma unroll 1
        for (int c = 0; c < 5; c++) {
          mbar_wait(bars + 8 * (B_YST + c), 0);
          asm volatile("cp.async.bulk.global.shared::cta.bulk_group [%0], [%1], 4096;\ncp.async.bulk.commit_group;"
                       ::"l"(g_Y + (5 * b + c) * Y_PITCH), "r"(sb + off_ch(c)) : "memory");
          if (c == 2) {
            asm volatile("cp.async.bulk.wait_group.read 0;" ::: "memory");
            mbar_arrive(bars + 8 * B_C34);
          }
        }
        asm volatile("cp.async.bulk.wait_group 0;\nfence.proxy.async.global;" ::: "memory");
        TS(75);
        if (!(NOMB & 2)) asm volatile("fence.release.gpu;" ::: "memory");
        flag_bump(g_cnt + C_Y + 32 * (b >> 4));
        TS(27);
        mbar_arrive(bars + 8 * B_YSIG);
        mbar_expect_tx(bars + 8 * B_YFULL, 20480);
        flag_wait(g_cnt + C_Y + 32 * hg, (lds32(sb + OFF_EPOCH) + 1) * 16);
        TS(24);
        tma_2d(sb + OFF_YT, &m.y, 128 * r, 80 * hg, bars + 8 * B_YFULL);
        tma_2d(sb + OFF_YT + 10240, &m.y, 128 * r + 64, 80 * hg, bars + 8 * B_YFULL);
      }
    }
  } else {
    asm volatile("setmaxnreg.inc.sync.aligned.u32 152;");
    if (wg < 2) {
      float acc[120];
#pragma unroll
      for (int i = 0; i < 120; i++) acc[i] = 0.f;
      const uint32_t da = desc_lo(sb + wg * 8192, 16), db = desc_lo(sb + ST_W, 8192), dc = desc_lo(sb + ST_WT, 2048);
      if (PW1) pin<120>(acc);
      if (PW1 == 2) mbar_wait(bars + 8 * B_FULL1, 0);
#pragma unroll 1
      for (int kb = 0; kb < 10; kb++) {
        mbar_wait(bars + 8 * (B_FULL1 + (kb & 3)), (kb >> 2) & 1);
        const uint32_t so = (kb & 3) * (STAGE_BYTES >> 4);
        wg_fence();
#pragma unroll
        for (int k = 0; k < 4; k++) {
          WgSST<192>::mma<HI_SW128, HI_SW128>(acc, da + so + 2 * k, db + so + 128 * k, 1);
          WgSST<48>::mma<HI_SW128, HI_SW32>(acc + 96, da + so + 2 * k, dc + so + 32 * k, 1);
        }
        wg_commit();
        wg_wait<1>();
        if (kb > 0 && lane == 0) mbar_arrive(bars + 8 * (kb == 4 ? B_E3 : B_EMPTY1 + ((kb - 1) & 3)));
      }
      wg_wait<0>();
      pin<120>(acc);
      if (lane == 0) mbar_arrive(bars + 8 * B_P1);
      TSM(w == 0, 3 + wg);
      attention(acc, sb, b, wg, w, lane);
    } else {
      const int tw = tid & 127, chl = 64 * (b & 1) + 8 * w + (lane >> 2);
      uint4* up = g_U + chl * U_PITCH + ((4 * (b >> 1) + (lane & 3)) ^ ((b >> 2) & 1));
      uint2 sw[10];
      uint32_t dv = 0;
      if (lane < 5) dv = __ldg(reinterpret_cast<const unsigned short*>(p.ssm_D) + 5 * b + lane);
#pragma unroll
      for (int i = 0; i < 10; i++) sw[i] = ldg64(reinterpret_cast<const uint2*>(p.shift_k) + chl + 128 * (i >> 1) + 32 * (i & 1));
      uint32_t tab[12];
      fft_tables(tab, tw);
      uint4 res[10];
#pragma unroll
      for (int i = 0; i < 10; i++) res[i] = make_uint4(0, 0, 0, 0);
#pragma unroll 1
      for (int slab = 0; slab < 5; slab++) {
#pragma unroll
        for (int i = 0; i < 8; i++) res[i] = res[i + 2];
        prep_slab(res + 8, sw, sb, slab, w, lane);
        TSIF(w == 0, 99 + 4 * slab);
#pragma unroll
        for (int i = 0; i < 8; i++) sw[i] = sw[i + 2];
      }
      TSIF(w == 0, 28);
      __syncwarp();
      if (lane == 0) mbar_arrive(bars + 8 * B_KVD + ((res[8].x ^ res[9].x) & p.zero));
      mbar_wait(bars + 8 * B_KVD, 0);
      fft_tables_store(tab, sb, tw);
      mbar_wait(bars + 8 * B_LAST, 0);
#pragma unroll
      for (int i = 0; i < 10; i++) up[(128 * (i >> 1) + 32 * (i & 1)) * U_PITCH] = res[i];
      __syncwarp();
      if (lane == 0) mbar_arrive(bars + 8 * B_PREP);
      TSIF(w == 0, 5);
      mbar_wait(bars + 8 * (G_AFTER ? B_USIG : B_LAST), 0);
      prep_gate(p, b, w, lane);
      __syncwarp();
      if (lane == 0) mbar_arrive(bars + 8 * B_GATE);
      TSIF(w == 0, 72);
      mbar_wait(bars + 8 * B_HB, 0);
      TSIF(w == 0, 123);
      const uint32_t ha = sb + U_BYTES + ((tw >> 3) * 16 + 8 + (tw & 7)) * 16;
      uint4 hv[5];
#pragma unroll
      for (int c = 0; c < 5; c++) hv[c] = lds128(ha + off_ch(c));
      __syncwarp();
#pragma unroll
      for (int c = 0; c < 5; c++) sts128((ha ^ 16) + off_ch(c), hv[c].x, hv[c].y, hv[c].z, hv[c].w);
      if (tw < 5) asm volatile("st.shared.f32 [%0], %1;" ::"r"(sb + OFF_D + 4 * tw), "f"(bf_lo(dv) * 0.125f) : "memory");
      fence_async_smem();
      __syncwarp();
      if (lane == 0) mbar_arrive(bars + 8 * B_HA);
      TSIF(w == 0, 6);
    }

    FftConst fc;
    fft_twiddles(fc, w, lane);
    mbar_wait(bars + 8 * B_HA, 0);
    fft_matrices(fc, sb, w, lane);
    if (ATT_GATE && !H_EARLY) mbar_wait(bars + 8 * B_ATTN, 0);
    TSIF(w == 0 && wg == 2, 124);
#pragma unroll 1
    for (int c = wg == 2 ? 0 : wg + 1; c < 5; c += 3) {
      conv_channel(fc, sb, c, wg, w, lane);
      if (lane == 0) mbar_arrive(bars + 8 * (B_YST + c));
      TSM(w == 0, 10 + c);
    }

    if (wg < 2) {
      const int g = lane >> 2;
      float acc[40];
#pragma unroll
      for (int i = 0; i < 40; i++) acc[i] = 0.f;
      const uint32_t da = desc_lo(sb + wg * 1024, 2048), db = desc_lo(sb, 2560);
      mbar_wait(bars + 8 * B_ATTN, 0);
      mbar_wait(bars + 8 * (B_YST + 3), 0);
      mbar_wait(bars + 8 * (B_YST + 4), 0);
      if (PW2) mbar_wait(bars + 8 * B_FULL2, 0);
#pragma unroll 1
      for (int j = 0; j < 8; j++) {
        mbar_wait(bars + 8 * (B_FULL2 + j), 0);
        const uint32_t oa = da + (off_o(j) >> 4), ob = db + (off_w(j) >> 4);
        wg_fence();
#pragma unroll
        for (int k = 0; k < 5; k++) WgSST<80>::mma<HI_NONE, HI_SW32>(acc, oa + 256 * k, ob + 32 * k, 1);
        wg_commit();
        wg_wait<1>();
        if (j >= 1 && j <= 4 && lane == 0) mbar_arrive(bars + 8 * (B_EMPTY2 + j - 1));
      }
      TSIF(w == 0 && wg == 0, 113);
      const int tr = 64 * wg + 16 * w + (lane & 15);
      const uint32_t fm = sb + OFF_QS + tr * 128, fx = (lane >> 4) ^ (tr & 7);
      const uint32_t ft = sb + OFF_QT + tr * 32 + (((lane >> 4) ^ (tr >> 2)) & 1) * 16;
      const float g0 = __uint_as_float(lds32(sb + OFF_GATE + (64 * wg + 16 * w + g) * 4));
      const float g1 = __uint_as_float(lds32(sb + OFF_GATE + (64 * wg + 16 * w + 8 + g) * 4));
      const uint32_t ga = pack2(g0, g0), gb = pack2(g1, g1);
      const uint32_t na = pack2(1.f - g0, 1.f - g0), nb = pack2(1.f - g1, 1.f - g1);

      wg_wait<0>();
      pin<40>(acc);
      TSM(w == 0, 17 + wg);
      uint32_t pb[20];
#pragma unroll
      for (int j = 0; j < 10; j++) {
        pb[2 * j] = bmul(na, pack2(acc[4 * j], acc[4 * j + 1]));
        pb[2 * j + 1] = bmul(nb, pack2(acc[4 * j + 2], acc[4 * j + 3]));
        asm volatile("" : "+r"(pb[2 * j]), "+r"(pb[2 * j + 1]));
      }
      const uint32_t ya = sb + OFF_YT + wg * 10240 + ((lane >> 4) * 8 + (lane & 7)) * 128 +
                          (((2 * w + (((lane >> 3) & 1) ^ wg)) ^ (lane & 7)) << 4);
      uint32_t qf[20];
      mbar_wait(bars + 8 * B_QF, 0);
#pragma unroll
      for (int j = 0; j < 5; j++) ldsm4(qf + 4 * j, j < 4 ? fm + ((fx ^ (2 * j)) << 4) : ft);
      mbar_wait(bars + 8 * B_YFULL, 0);
      TSIF(w == 0 && wg == 0, 19);
#pragma unroll
      for (int j = 0; j < 5; j++) {
        uint32_t y[4];
        ldsm4t(y, ya + 2048 * j);
#pragma unroll
        for (int i = 0; i < 4; i++) qf[4 * j + i] = badd(bmul((i & 1) ? gb : ga, bmul(qf[4 * j + i], y[i])), pb[4 * j + i]);
      }
#pragma unroll
      for (int j = 0; j < 5; j++) stsm4(j < 4 ? fm + ((fx ^ (2 * j)) << 4) : ft, qf + 4 * j);
      fence_async_smem();
      __syncwarp();
      if (lane == 0) {
        const int row = 64 * wg + 16 * w;
        asm volatile("cp.async.bulk.tensor.2d.global.shared::cta.bulk_group [%0, {%2, %3}], [%1];"
                     ::"l"(&m.om), "r"(sb + OFF_QS + row * 128), "r"(80 * hg), "r"(128 * r + row) : "memory");
        asm volatile("cp.async.bulk.tensor.2d.global.shared::cta.bulk_group [%0, {%2, %3}], [%1];"
                     ::"l"(&m.ot), "r"(sb + OFF_QT + row * 32), "r"(80 * hg + 64), "r"(128 * r + row) : "memory");
        asm volatile("cp.async.bulk.commit_group;\ncp.async.bulk.wait_group.read 0;" ::: "memory");
      }
      TSM(true, 40 + 4 * wg + w);
      if (ENDBAR) asm volatile("bar.sync 15, 256;" ::: "memory");
    }
  }
}

typedef CUresult (*EncodeFn)(CUtensorMap*, CUtensorMapDataType, cuuint32_t, void*, const cuuint64_t*, const cuuint64_t*,
                             const cuuint32_t*, const cuuint32_t*, CUtensorMapInterleave, CUtensorMapSwizzle,
                             CUtensorMapL2promotion, CUtensorMapFloatOOBfill);

void encode(EncodeFn fn, CUtensorMap* tm, const void* base, int rank, const cuuint64_t* dims, const cuuint64_t* strides,
            const cuuint32_t* box, CUtensorMapSwizzle swz) {
  const cuuint32_t ones[3] = {1, 1, 1};
  fn(tm, CU_TENSOR_MAP_DATA_TYPE_BFLOAT16, rank, const_cast<void*>(base), dims, strides, box, ones,
     CU_TENSOR_MAP_INTERLEAVE_NONE, swz, CU_TENSOR_MAP_L2_PROMOTION_L2_128B, CU_TENSOR_MAP_FLOAT_OOB_FILL_NONE);
}

}

extern "C" void kernel_launch(void* const* d_in, const int* in_sizes, int n_in, void* d_out, int out_size) {
  (void)in_sizes; (void)n_in; (void)out_size;
  Params p;
  p.q = (const __nv_bfloat16*)d_in[0];
  p.k = (const __nv_bfloat16*)d_in[1];
  p.v = (const __nv_bfloat16*)d_in[2];
  p.shift_k = (const __nv_bfloat16*)d_in[3];
  p.ssm_k = (const __nv_bfloat16*)d_in[4];
  p.ssm_D = (const __nv_bfloat16*)d_in[5];
  p.wqkv = (const __nv_bfloat16*)d_in[7];
  p.wo = (const __nv_bfloat16*)d_in[8];
  p.gate_w = (const __nv_bfloat16*)d_in[9];
  p.out = (__nv_bfloat16*)d_out;
  p.zero = 0;

  static EncodeFn fn = nullptr;
  static void* yaddr = nullptr;
  if (!fn) {
    cudaDriverEntryPointQueryResult qr;
    void* f = nullptr;
    cudaGetDriverEntryPoint("cuTensorMapEncodeTiled", &f, cudaEnableDefault, &qr);
    fn = (EncodeFn)f;
    cudaGetSymbolAddress(&yaddr, g_Y);
    cudaFuncSetAttribute(fused_kernel, cudaFuncAttributeMaxDynamicSharedMemorySize, SMEM_BYTES);
  }
  Maps m;
  {
    const cuuint64_t dims[3] = {640, 1024, 2}, st[2] = {2560, 1280};
    const cuuint32_t box[3] = {64, 64, 2};
    encode(fn, &m.x, p.q, 3, dims, st, box, CU_TENSOR_MAP_SWIZZLE_128B);
  }
  {
    const cuuint64_t dims[3] = {640, 640, 3}, st[2] = {3840, 1280};
    const cuuint32_t box[3] = {64, 64, 3}, boxt[3] = {16, 64, 3};
    encode(fn, &m.wm, p.wqkv, 3, dims, st, box, CU_TENSOR_MAP_SWIZZLE_128B);
    encode(fn, &m.wt, p.wqkv, 3, dims, st, boxt, CU_TENSOR_MAP_SWIZZLE_32B);
  }
  {
    const cuuint64_t dims[3] = {64, 2048, 10}, st[2] = {1280, 128};
    const cuuint32_t boxk[3] = {64, 35, 1}, boxv[3] = {64, 32, 1};
    encode(fn, &m.k, p.k, 3, dims, st, boxk, CU_TENSOR_MAP_SWIZZLE_128B);
    encode(fn, &m.v, p.v, 3, dims, st, boxv, CU_TENSOR_MAP_SWIZZLE_128B);
  }
  {
    const cuuint64_t dims[3] = {16, 640, 40}, st[2] = {1280, 32};
    const cuuint32_t box[3] = {16, 40, 5};
    encode(fn, &m.wo, p.wo, 3, dims, st, box, CU_TENSOR_MAP_SWIZZLE_32B);
  }
  {
    const cuuint64_t dims[2] = {2048, 640}, st[1] = {Y_PITCH * 16};
    const cuuint32_t box[2] = {64, 80};
    encode(fn, &m.y, yaddr, 2, dims, st, box, CU_TENSOR_MAP_SWIZZLE_128B);
  }
  {
    const cuuint64_t dims[2] = {640, 2048}, st[1] = {1280};
    const cuuint32_t bqm[2] = {64, 128}, bqt[2] = {16, 128}, bom[2] = {64, 16}, bot[2] = {16, 16};
    encode(fn, &m.qm, p.q, 2, dims, st, bqm, CU_TENSOR_MAP_SWIZZLE_128B);
    encode(fn, &m.qt, p.q, 2, dims, st, bqt, CU_TENSOR_MAP_SWIZZLE_32B);
    encode(fn, &m.om, p.out, 2, dims, st, bom, CU_TENSOR_MAP_SWIZZLE_128B);
    encode(fn, &m.ot, p.out, 2, dims, st, bot, CU_TENSOR_MAP_SWIZZLE_32B);
  }
  fused_kernel<<<NCTA, NTHR, SMEM_BYTES>>>(m, p);
}
```

```cpp
#include <cuda.h>
#include <cuda_bf16.h>
#include <cuda_runtime.h>
#include <stdint.h>

namespace {

constexpr int SEQ = 2048, DIM = 640, NCTA = 128, NTHR = 512;

#define TRIG_KB 9
#define KV_KB 2
#define DEV_EXIT 0
#define ATT_GATE 1
#define G_AFTER 0
#define FENCE_LO 0
#define FENCE_HI 0
#define PW1 2
#define PW2 1
#define ENDBAR 0
#define PAD_KB 0
#define Y_ALIAS 1
#define WO_LSU 0
#define WP_TRIG (B_KV + 4)
#define NOMB 0
#define SRC_ROT 0
#define WAIT_NS 0
#define WB_TRIG B_USIG
#define G_POS 0
#define TAILF 1
#define T_ISSUE 384
#define T_PF 416
#define T_INIT 448
#define ATT_MERGE 0
#define BMAP 1
#define PRE2 1
#define KV_MIX 0
#define O_DEFER 0
#define HORD(i) ((0x43021 >> (4 * (i))) & 7)
#define H_PIN 1
#define RF_GATE 0
#define WO_TRIG B_WST
#define WL_TRIG B_WOP
#define WO_GATE 1

constexpr uint32_t STAGE_BYTES = 47104, ST_W = 16384, ST_WT = 40960;
constexpr uint32_t O_BYTES = 20480, WO_BYTES = 12800;
constexpr uint32_t OFF_OA = 0;
constexpr uint32_t OFF_QS = 3 * O_BYTES, OFF_QT = OFF_QS + 16384;
constexpr uint32_t OFF_WC = 81920;
constexpr uint32_t OFF_WA = 94720;
constexpr uint32_t OFF_GATE = 145920;
constexpr uint32_t OFF_KVX = 147968;
constexpr uint32_t OFF_D = OFF_GATE + 512;
constexpr uint32_t OFF_CH3 = 163840;
constexpr uint32_t CH_BYTES = 12288, U_BYTES = 4096;
constexpr uint32_t OFF_FT = 225280, OFF_GT = 229376;
constexpr uint32_t OFF_CH0 = 188416;
constexpr uint32_t OFF_KVS = OFF_CH0, KVS_V = 4480, KVS_BYTES = 8576;
constexpr uint32_t OFF_WS = OFF_WA;
constexpr uint32_t OFF_YT = 163840;
constexpr uint32_t OFF_BAR = 231936;
constexpr uint32_t SMEM_BYTES = OFF_BAR + 512;

enum : uint32_t {
  B_FULL1 = 0, B_EMPTY1 = 4, B_S3 = 7, B_FULL2 = 52, B_EMPTY2 = 13, B_U = 8, B_GATE = 12, B_HA = 19, B_HB = 20,
  B_ATTN = 21, B_C34 = 22, B_CONV = 23, B_YFULL = 24, B_EPOCH = 25, B_PREP = 26, B_P1 = 27, B_LAST = 28,
  B_E3 = 29, B_OSIG = 30, B_WOP = 31, B_USIG = 32, B_WST = 33, B_KV = 34, B_KVD = 39, B_HC = 61, B_QF = 62, B_YST = 40,
  B_H = 45, B_YSIG = 50
};
constexpr uint32_t OFF_EPOCH = OFF_BAR + 8 * 51;
__device__ __forceinline__ uint32_t off_o(int j) { return j < 4 ? OFF_OA + j * O_BYTES : j < 6 ? OFF_CH0 + (j - 4) * O_BYTES : OFF_OA + (j - 6) * O_BYTES; }
__device__ __forceinline__ uint32_t off_w(int j) { return j < 4 ? OFF_WA + j * WO_BYTES : j == 4 ? OFF_KVX : j == 5 ? OFF_WC : OFF_WA + (j - 6) * WO_BYTES; }
__device__ __forceinline__ int step_src(int hg, int j) { return SRC_ROT ? (hg + j) & 7 : j == 0 ? hg : j <= hg ? j - 1 : j; }
__device__ __forceinline__ bool tail_first(int hg) { return TAILF && (hg & 3) == 3; }
__device__ __forceinline__ uint32_t off_ch(int c) { return (c < 3 ? OFF_CH0 : OFF_CH3 - 3 * CH_BYTES) + c * CH_BYTES; }

#define U_PITCH 264
__device__ __align__(1024) uint4 g_U[DIM * U_PITCH];
__device__ uint4 g_O[NCTA * 1280];
#define g_Y g_U
constexpr int Y_PITCH = U_PITCH;
__device__ uint4 g_WO[64 * 800];
__device__ uint4 g_halo[NCTA * 2 * 7 * 32];
__device__ float g_gate[SEQ + PAD_KB * 256];
__device__ unsigned g_cnt[32 * (1 + 2 * 16 + 8 + NCTA)];
constexpr int C_LAUNCH = 0, C_PREP = 32, C_Y = 32 * 17, C_W = 32 * 33, C_O = 32 * 41;

#define TSM(cond, slot) do { } while (0)
#define TSIF(cond, slot) do { if (__LINE__ >= FENCE_LO && __LINE__ < FENCE_HI) sched_fence(); } while (0)
__device__ __forceinline__ void sched_fence() {
  asm volatile("{\n.reg .pred p;\n.reg .u32 c;\nmov.u32 c, %%clock;\nsetp.eq.u32 p, c, 0;\n@p st.shared.u32 [%0], c;\n}"
               ::"r"(1024 + OFF_EPOCH + 4) : "memory");
}
#define TS(slot) TSIF(true, slot)

struct Params {
  const __nv_bfloat16 *q, *k, *v, *shift_k, *ssm_k, *ssm_D, *wqkv, *wo, *gate_w;
  __nv_bfloat16* out;
  uint32_t zero;
};

#define POLL_NS 0
constexpr int SPIN_LIMIT = 1 << 17;

__device__ __forceinline__ void mbar_init(uint32_t bar, uint32_t count) {
  asm volatile("mbarrier.init.shared::cta.b64 [%0], %1;" ::"r"(bar), "r"(count) : "memory");
}
__device__ __forceinline__ void mbar_expect_tx(uint32_t bar, uint32_t bytes) {
  asm volatile("mbarrier.arrive.expect_tx.shared::cta.b64 _, [%0], %1;" ::"r"(bar), "r"(bytes) : "memory");
}
__device__ __forceinline__ void mbar_arrive(uint32_t bar) {
  asm volatile("mbarrier.arrive.shared::cta.b64 _, [%0];" ::"r"(bar) : "memory");
}
__device__ __forceinline__ void mbar_wait(uint32_t bar, uint32_t parity) {
  uint32_t ok;
  int spins = 0;
  do {
    if (WAIT_NS)
      asm volatile("{\n.reg .pred p;\nmbarrier.try_wait.parity.shared::cta.b64 p, [%1], %2, %3;\nselp.b32 %0, 1, 0, p;\n}"
                   : "=r"(ok) : "r"(bar), "r"(parity), "r"(WAIT_NS) : "memory");
    else
      asm volatile("{\n.reg .pred p;\nmbarrier.try_wait.parity.shared::cta.b64 p, [%1], %2;\nselp.b32 %0, 1, 0, p;\n}"
                   : "=r"(ok) : "r"(bar), "r"(parity) : "memory");
    if (++spins > SPIN_LIMIT) break;
  } while (!ok);
}
__device__ __forceinline__ void flag_poll(const unsigned* p, unsigned target) {
  unsigned v;
  int spins = 0;
  do {
    if (POLL_NS && spins) __nanosleep(POLL_NS);
    asm volatile("ld.relaxed.gpu.global.u32 %0, [%1];" : "=r"(v) : "l"(p) : "memory");
    if (++spins > SPIN_LIMIT) break;
  } while ((int)(v - target) < 0);
}
__device__ __forceinline__ void flag_wait(const unsigned* p, unsigned target) {
  flag_poll(p, target);
  asm volatile("fence.acquire.gpu;\nfence.proxy.async.global;" ::: "memory");
}
__device__ __forceinline__ void flag_signal(unsigned* p, int n, int lane) {
  if (lane == 0) asm volatile("fence.release.gpu;" ::: "memory");
  __syncwarp();
  if (lane < n) asm volatile("red.relaxed.gpu.global.add.u32 [%0], 1;" ::"l"(p + 32 * lane) : "memory");
}
__device__ __forceinline__ void flag_bump(unsigned* p) {
  asm volatile("red.relaxed.gpu.global.add.u32 [%0], 1;" ::"l"(p) : "memory");
}
__device__ __forceinline__ void fence_async_smem() { asm volatile("fence.proxy.async.shared::cta;" ::: "memory"); }
__device__ __forceinline__ void wg_sync(int id) { asm volatile("bar.sync %0, 128;" ::"r"(id) : "memory"); }

__device__ __forceinline__ void tma_2d(uint32_t dst, const CUtensorMap* tm, int c0, int c1, uint32_t bar) {
  asm volatile("cp.async.bulk.tensor.2d.shared::cluster.global.mbarrier::complete_tx::bytes [%0], [%1, {%3, %4}], [%2];"
               ::"r"(dst), "l"(tm), "r"(bar), "r"(c0), "r"(c1) : "memory");
}
__device__ __forceinline__ void tma_3d(uint32_t dst, const CUtensorMap* tm, int c0, int c1, int c2, uint32_t bar) {
  asm volatile("cp.async.bulk.tensor.3d.shared::cluster.global.mbarrier::complete_tx::bytes [%0], [%1, {%3, %4, %5}], [%2];"
               ::"r"(dst), "l"(tm), "r"(bar), "r"(c0), "r"(c1), "r"(c2) : "memory");
}
__device__ __forceinline__ void bulk_load(uint32_t dst, const void* src, uint32_t bytes, uint32_t bar) {
  asm volatile("cp.async.bulk.shared::cluster.global.mbarrier::complete_tx::bytes [%0], [%1], %2, [%3];"
               ::"r"(dst), "l"(src), "r"(bytes), "r"(bar) : "memory");
}
__device__ __forceinline__ void tm_prefetch(const CUtensorMap* tm) {
  asm volatile("prefetch.tensormap [%0];" ::"l"(tm) : "memory");
}

__device__ __forceinline__ void wg_fence() { asm volatile("wgmma.fence.sync.aligned;" ::: "memory"); }
__device__ __forceinline__ void wg_commit() { asm volatile("wgmma.commit_group.sync.aligned;" ::: "memory"); }
template <int N> __device__ __forceinline__ void wg_wait() { asm volatile("wgmma.wait_group.sync.aligned %0;" ::"n"(N) : "memory"); }
__device__ __forceinline__ uint32_t desc_lo(uint32_t addr, uint32_t lbo) { return ((addr & 0x3FFFF) >> 4) | ((lbo >> 4) << 16); }
constexpr uint32_t desc_hi(uint32_t sbo, uint32_t swz) { return (sbo >> 4) | (swz << 30); }
constexpr uint32_t HI_SW128 = desc_hi(1024, 1), HI_SW64 = desc_hi(512, 2), HI_SW32 = desc_hi(256, 3), HI_NONE = desc_hi(128, 0);
template <int N> __device__ __forceinline__ void pin(float* d) {
#pragma unroll
  for (int i = 0; i < N; i++) asm volatile("" : "+f"(d[i])::"memory");
}

__device__ __forceinline__ uint32_t lds32(uint32_t a) {
  uint32_t v;
  asm volatile("ld.volatile.shared.u32 %0, [%1];" : "=r"(v) : "r"(a) : "memory");
  return v;
}
__device__ __forceinline__ uint4 ldg128(const void* a) {
  uint4 v;
  asm volatile("ld.global.nc.v4.u32 {%0, %1, %2, %3}, [%4];" : "=r"(v.x), "=r"(v.y), "=r"(v.z), "=r"(v.w) : "l"(a) : "memory");
  return v;
}
__device__ __forceinline__ uint2 ldg64(const void* a) {
  uint2 v;
  asm volatile("ld.global.nc.v2.u32 {%0, %1}, [%2];" : "=r"(v.x), "=r"(v.y) : "l"(a) : "memory");
  return v;
}
__device__ __forceinline__ void ldsm4(uint32_t* r, uint32_t a) {
  asm volatile("ldmatrix.sync.aligned.m8n8.x4.shared.b16 {%0, %1, %2, %3}, [%4];"
               : "=r"(r[0]), "=r"(r[1]), "=r"(r[2]), "=r"(r[3]) : "r"(a) : "memory");
}
__device__ __forceinline__ void ldsm4t(uint32_t* r, uint32_t a) {
  asm volatile("ldmatrix.sync.aligned.m8n8.x4.trans.shared.b16 {%0, %1, %2, %3}, [%4];"
               : "=r"(r[0]), "=r"(r[1]), "=r"(r[2]), "=r"(r[3]) : "r"(a) : "memory");
}
__device__ __forceinline__ uint4 lds128(uint32_t a) {
  uint4 v;
  asm volatile("ld.shared.v4.u32 {%0, %1, %2, %3}, [%4];" : "=r"(v.x), "=r"(v.y), "=r"(v.z), "=r"(v.w) : "r"(a) : "memory");
  return v;
}
__device__ __forceinline__ void sts128(uint32_t a, uint32_t x, uint32_t y, uint32_t z, uint32_t w) {
  asm volatile("st.shared.v4.u32 [%0], {%1, %2, %3, %4};" ::"r"(a), "r"(x), "r"(y), "r"(z), "r"(w) : "memory");
}
__device__ __forceinline__ void stsm4(uint32_t a, const uint32_t* r) {
  asm volatile("stmatrix.sync.aligned.m8n8.x4.shared.b16 [%0], {%1, %2, %3, %4};" ::"r"(a), "r"(r[0]), "r"(r[1]), "r"(r[2]), "r"(r[3]) : "memory");
}
__device__ __forceinline__ void stsm4t(uint32_t a, const uint32_t* r) {
  asm volatile("stmatrix.sync.aligned.m8n8.x4.trans.shared.b16 [%0], {%1, %2, %3, %4};" ::"r"(a), "r"(r[0]), "r"(r[1]), "r"(r[2]), "r"(r[3]) : "memory");
}
__device__ __forceinline__ uint32_t pack2(float lo, float hi) {
  uint32_t r;
  asm("cvt.rn.bf16x2.f32 %0, %1, %2;" : "=r"(r) : "f"(hi), "f"(lo));
  return r;
}
__device__ __forceinline__ uint32_t movm(uint32_t a) {
  uint32_t d;
  asm volatile("movmatrix.sync.aligned.m8n8.trans.b16 %0, %1;" : "=r"(d) : "r"(a));
  return d;
}
__device__ __forceinline__ uint32_t bmul(uint32_t a, uint32_t b) {
  uint32_t d;
  asm("mul.rn.bf16x2 %0, %1, %2;" : "=r"(d) : "r"(a), "r"(b));
  return d;
}
__device__ __forceinline__ uint32_t badd(uint32_t a, uint32_t b) {
  uint32_t d;
  asm("add.rn.bf16x2 %0, %1, %2;" : "=r"(d) : "r"(a), "r"(b));
  return d;
}
__device__ __forceinline__ float bf_lo(uint32_t x) { return __uint_as_float(x << 16); }
__device__ __forceinline__ float bf_hi(uint32_t x) { return __uint_as_float(x & 0xFFFF0000u); }
__device__ __forceinline__ float ex2(float x) {
  float y;
  asm("ex2.approx.ftz.f32 %0, %1;" : "=f"(y) : "f"(x));
  return y;
}
__device__ __forceinline__ float rcp(float x) {
  float y;
  asm("rcp.approx.ftz.f32 %0, %1;" : "=f"(y) : "f"(x));
  return y;
}
__device__ __forceinline__ void mma16816(float* d, uint32_t a0, uint32_t a1, uint32_t a2, uint32_t a3, uint32_t b0, uint32_t b1) {
  asm volatile("mma.sync.aligned.m16n8k16.row.col.f32.bf16.bf16.f32 {%0, %1, %2, %3}, {%4, %5, %6, %7}, {%8, %9}, {%0, %1, %2, %3};"
               : "+f"(d[0]), "+f"(d[1]), "+f"(d[2]), "+f"(d[3])
               : "r"(a0), "r"(a1), "r"(a2), "r"(a3), "r"(b0), "r"(b1));
}
__device__ __forceinline__ void mma1688(float* d, uint32_t a0, uint32_t a1, uint32_t b0) {
  asm volatile("mma.sync.aligned.m16n8k8.row.col.f32.bf16.bf16.f32 {%0, %1, %2, %3}, {%4, %5}, {%6}, {%0, %1, %2, %3};"
               : "+f"(d[0]), "+f"(d[1]), "+f"(d[2]), "+f"(d[3])
               : "r"(a0), "r"(a1), "r"(b0));
}

template <int N> struct WgRS;
template <int N> struct WgSST;
template <> struct WgRS<32> {
  template <uint32_t HB>
  static __device__ __forceinline__ void mma(float* d, const uint32_t* a, uint32_t db) {
    asm volatile("{\n.reg .pred p;\n.reg .b64 db;\nsetp.ne.b32 p, %22, 0;\n"
      "mov.b64 db, {%20, %21};\n"
      "wgmma.mma_async.sync.aligned.m64n32k16.f32.bf16.bf16 {"
      "%0, %1, %2, %3, %4, %5, %6, %7, %8, %9, %10, %11, %12, %13, %14, %15"
      "}, {%16, %17, %18, %19}, db, p, 1, 1, 1;\n}\n"
      : "+f"(d[0]), "+f"(d[1]), "+f"(d[2]), "+f"(d[3]), "+f"(d[4]), "+f"(d[5]), "+f"(d[6]), "+f"(d[7]),
        "+f"(d[8]), "+f"(d[9]), "+f"(d[10]), "+f"(d[11]), "+f"(d[12]), "+f"(d[13]), "+f"(d[14]), "+f"(d[15])
      : "r"(a[0]), "r"(a[1]), "r"(a[2]), "r"(a[3]), "r"(db), "n"(HB), "n"(1));
  }
  template <uint32_t HB>
  static __device__ __forceinline__ void set(float* d, const uint32_t* a, uint32_t db) {
    asm volatile("{\n.reg .pred p;\n.reg .b64 db;\nsetp.ne.b32 p, %22, 0;\n"
      "mov.b64 db, {%20, %21};\n"
      "wgmma.mma_async.sync.aligned.m64n32k16.f32.bf16.bf16 {"
      "%0, %1, %2, %3, %4, %5, %6, %7, %8, %9, %10, %11, %12, %13, %14, %15"
      "}, {%16, %17, %18, %19}, db, p, 1, 1, 1;\n}\n"
      : "=f"(d[0]), "=f"(d[1]), "=f"(d[2]), "=f"(d[3]), "=f"(d[4]), "=f"(d[5]), "=f"(d[6]), "=f"(d[7]),
        "=f"(d[8]), "=f"(d[9]), "=f"(d[10]), "=f"(d[11]), "=f"(d[12]), "=f"(d[13]), "=f"(d[14]), "=f"(d[15])
      : "r"(a[0]), "r"(a[1]), "r"(a[2]), "r"(a[3]), "r"(db), "n"(HB), "n"(0));
  }
};
template <> struct WgRS<64> {
  template <uint32_t HB>
  static __device__ __forceinline__ void mma(float* d, const uint32_t* a, uint32_t db) {
    asm volatile("{\n.reg .pred p;\n.reg .b64 db;\nsetp.ne.b32 p, %38, 0;\n"
      "mov.b64 db, {%36, %37};\n"
      "wgmma.mma_async.sync.aligned.m64n64k16.f32.bf16.bf16 {"
      "%0, %1, %2, %3, %4, %5, %6, %7, %8, %9, %10, %11, %12, %13, %14, %15, "
      "%16, %17, %18, %19, %20, %21, %22, %23, %24, %25, %26, %27, %28, %29, %30, %31"
      "}, {%32, %33, %34, %35}, db, p, 1, 1, 1;\n}\n"
      : "+f"(d[0]), "+f"(d[1]), "+f"(d[2]), "+f"(d[3]), "+f"(d[4]), "+f"(d[5]), "+f"(d[6]), "+f"(d[7]),
        "+f"(d[8]), "+f"(d[9]), "+f"(d[10]), "+f"(d[11]), "+f"(d[12]), "+f"(d[13]), "+f"(d[14]), "+f"(d[15]),
        "+f"(d[16]), "+f"(d[17]), "+f"(d[18]), "+f"(d[19]), "+f"(d[20]), "+f"(d[21]), "+f"(d[22]), "+f"(d[23]),
        "+f"(d[24]), "+f"(d[25]), "+f"(d[26]), "+f"(d[27]), "+f"(d[28]), "+f"(d[29]), "+f"(d[30]), "+f"(d[31])
      : "r"(a[0]), "r"(a[1]), "r"(a[2]), "r"(a[3]), "r"(db), "n"(HB), "n"(1));
  }
  template <uint32_t HB>
  static __device__ __forceinline__ void set(float* d, const uint32_t* a, uint32_t db) {
    asm volatile("{\n.reg .pred p;\n.reg .b64 db;\nsetp.ne.b32 p, %38, 0;\n"
      "mov.b64 db, {%36, %37};\n"
      "wgmma.mma_async.sync.aligned.m64n64k16.f32.bf16.bf16 {"
      "%0, %1, %2, %3, %4, %5, %6, %7, %8, %9, %10, %11, %12, %13, %14, %15, "
      "%16, %17, %18, %19, %20, %21, %22, %23, %24, %25, %26, %27, %28, %29, %30, %31"
      "}, {%32, %33, %34, %35}, db, p, 1, 1, 1;\n}\n"
      : "=f"(d[0]), "=f"(d[1]), "=f"(d[2]), "=f"(d[3]), "=f"(d[4]), "=f"(d[5]), "=f"(d[6]), "=f"(d[7]),
        "=f"(d[8]), "=f"(d[9]), "=f"(d[10]), "=f"(d[11]), "=f"(d[12]), "=f"(d[13]), "=f"(d[14]), "=f"(d[15]),
        "=f"(d[16]), "=f"(d[17]), "=f"(d[18]), "=f"(d[19]), "=f"(d[20]), "=f"(d[21]), "=f"(d[22]), "=f"(d[23]),
        "=f"(d[24]), "=f"(d[25]), "=f"(d[26]), "=f"(d[27]), "=f"(d[28]), "=f"(d[29]), "=f"(d[30]), "=f"(d[31])
      : "r"(a[0]), "r"(a[1]), "r"(a[2]), "r"(a[3]), "r"(db), "n"(HB), "n"(0));
  }
};
template <> struct WgSST<48> {
  template <uint32_t HA, uint32_t HB>
  static __device__ __forceinline__ void mma(float* d, uint32_t da, uint32_t db, int sc) {
    asm volatile("{\n.reg .pred p;\n.reg .b64 da, db;\nsetp.ne.b32 p, %28, 0;\n"
      "mov.b64 da, {%24, %25};\nmov.b64 db, {%26, %27};\n"
      "wgmma.mma_async.sync.aligned.m64n48k16.f32.bf16.bf16 {"
      "%0, %1, %2, %3, %4, %5, %6, %7, %8, %9, %10, %11, %12, %13, %14, %15, "
      "%16, %17, %18, %19, %20, %21, %22, %23"
      "}, da, db, p, 1, 1, 0, 1;\n}\n"
      : "+f"(d[0]), "+f"(d[1]), "+f"(d[2]), "+f"(d[3]), "+f"(d[4]), "+f"(d[5]), "+f"(d[6]), "+f"(d[7]),
        "+f"(d[8]), "+f"(d[9]), "+f"(d[10]), "+f"(d[11]), "+f"(d[12]), "+f"(d[13]), "+f"(d[14]), "+f"(d[15]),
        "+f"(d[16]), "+f"(d[17]), "+f"(d[18]), "+f"(d[19]), "+f"(d[20]), "+f"(d[21]), "+f"(d[22]), "+f"(d[23])
      : "r"(da), "n"(HA), "r"(db), "n"(HB), "r"(sc));
  }
};
template <> struct WgSST<80> {
  template <uint32_t HA, uint32_t HB>
  static __device__ __forceinline__ void mma(float* d, uint32_t da, uint32_t db, int sc) {
    asm volatile("{\n.reg .pred p;\n.reg .b64 da, db;\nsetp.ne.b32 p, %44, 0;\n"
      "mov.b64 da, {%40, %41};\nmov.b64 db, {%42, %43};\n"
      "wgmma.mma_async.sync.aligned.m64n80k16.f32.bf16.bf16 {"
      "%0, %1, %2, %3, %4, %5, %6, %7, %8, %9, %10, %11, %12, %13, %14, %15, "
      "%16, %17, %18, %19, %20, %21, %22, %23, %24, %25, %26, %27, %28, %29, %30, %31, "
      "%32, %33, %34, %35, %36, %37, %38, %39"
      "}, da, db, p, 1, 1, 0, 1;\n}\n"
      : "+f"(d[0]), "+f"(d[1]), "+f"(d[2]), "+f"(d[3]), "+f"(d[4]), "+f"(d[5]), "+f"(d[6]), "+f"(d[7]),
        "+f"(d[8]), "+f"(d[9]), "+f"(d[10]), "+f"(d[11]), "+f"(d[12]), "+f"(d[13]), "+f"(d[14]), "+f"(d[15]),
        "+f"(d[16]), "+f"(d[17]), "+f"(d[18]), "+f"(d[19]), "+f"(d[20]), "+f"(d[21]), "+f"(d[22]), "+f"(d[23]),
        "+f"(d[24]), "+f"(d[25]), "+f"(d[26]), "+f"(d[27]), "+f"(d[28]), "+f"(d[29]), "+f"(d[30]), "+f"(d[31]),
        "+f"(d[32]), "+f"(d[33]), "+f"(d[34]), "+f"(d[35]), "+f"(d[36]), "+f"(d[37]), "+f"(d[38]), "+f"(d[39])
      : "r"(da), "n"(HA), "r"(db), "n"(HB), "r"(sc));
  }
};
template <> struct WgSST<192> {
  template <uint32_t HA, uint32_t HB>
  static __device__ __forceinline__ void mma(float* d, uint32_t da, uint32_t db, int sc) {
    asm volatile("{\n.reg .pred p;\n.reg .b64 da, db;\nsetp.ne.b32 p, %100, 0;\n"
      "mov.b64 da, {%96, %97};\nmov.b64 db, {%98, %99};\n"
      "wgmma.mma_async.sync.aligned.m64n192k16.f32.bf16.bf16 {"
      "%0, %1, %2, %3, %4, %5, %6, %7, %8, %9, %10, %11, %12, %13, %14, %15, "
      "%16, %17, %18, %19, %20, %21, %22, %23, %24, %25, %26, %27, %28, %29, %30, %31, "
      "%32, %33, %34, %35, %36, %37, %38, %39, %40, %41, %42, %43, %44, %45, %46, %47, "
      "%48, %49, %50, %51, %52, %53, %54, %55, %56, %57, %58, %59, %60, %61, %62, %63, "
      "%64, %65, %66, %67, %68, %69, %70, %71, %72, %73, %74, %75, %76, %77, %78, %79, "
      "%80, %81, %82, %83, %84, %85, %86, %87, %88, %89, %90, %91, %92, %93, %94, %95"
      "}, da, db, p, 1, 1, 0, 1;\n}\n"
      : "+f"(d[0]), "+f"(d[1]), "+f"(d[2]), "+f"(d[3]), "+f"(d[4]), "+f"(d[5]), "+f"(d[6]), "+f"(d[7]),
        "+f"(d[8]), "+f"(d[9]), "+f"(d[10]), "+f"(d[11]), "+f"(d[12]), "+f"(d[13]), "+f"(d[14]), "+f"(d[15]),
        "+f"(d[16]), "+f"(d[17]), "+f"(d[18]), "+f"(d[19]), "+f"(d[20]), "+f"(d[21]), "+f"(d[22]), "+f"(d[23]),
        "+f"(d[24]), "+f"(d[25]), "+f"(d[26]), "+f"(d[27]), "+f"(d[28]), "+f"(d[29]), "+f"(d[30]), "+f"(d[31]),
        "+f"(d[32]), "+f"(d[33]), "+f"(d[34]), "+f"(d[35]), "+f"(d[36]), "+f"(d[37]), "+f"(d[38]), "+f"(d[39]),
        "+f"(d[40]), "+f"(d[41]), "+f"(d[42]), "+f"(d[43]), "+f"(d[44]), "+f"(d[45]), "+f"(d[46]), "+f"(d[47]),
        "+f"(d[48]), "+f"(d[49]), "+f"(d[50]), "+f"(d[51]), "+f"(d[52]), "+f"(d[53]), "+f"(d[54]), "+f"(d[55]),
        "+f"(d[56]), "+f"(d[57]), "+f"(d[58]), "+f"(d[59]), "+f"(d[60]), "+f"(d[61]), "+f"(d[62]), "+f"(d[63]),
        "+f"(d[64]), "+f"(d[65]), "+f"(d[66]), "+f"(d[67]), "+f"(d[68]), "+f"(d[69]), "+f"(d[70]), "+f"(d[71]),
        "+f"(d[72]), "+f"(d[73]), "+f"(d[74]), "+f"(d[75]), "+f"(d[76]), "+f"(d[77]), "+f"(d[78]), "+f"(d[79]),
        "+f"(d[80]), "+f"(d[81]), "+f"(d[82]), "+f"(d[83]), "+f"(d[84]), "+f"(d[85]), "+f"(d[86]), "+f"(d[87]),
        "+f"(d[88]), "+f"(d[89]), "+f"(d[90]), "+f"(d[91]), "+f"(d[92]), "+f"(d[93]), "+f"(d[94]), "+f"(d[95])
      : "r"(da), "n"(HA), "r"(db), "n"(HB), "r"(sc));
  }
};

struct FftConst {
  uint32_t f[2][4], fi[4][4];
  float ta[4], tb[4];
};
__device__ __forceinline__ void cis(int m, float scale, float& c, float& s) {
  const float a = (float)m * (-6.283185307179586f * scale);
  c = __cosf(a);
  s = __sinf(a);
}
__device__ __forceinline__ void fft_tables(uint32_t (&v)[12], int tw) {
  const int row = tw >> 2, ch = tw & 3;
#pragma unroll
  for (int i = 0; i < 4; i++) {
    float c[2], s[2], x[2];
#pragma unroll
    for (int e = 0; e < 2; e++) {
      cis((((32 * (8 * ch + 2 * i + e) + 15) * (4 * row - 63) + 2048) & 4095) - 2048, 1.f / 4096, c[e], s[e]);
      float gc, gs;
      cis((((row & 15) * (8 * (ch & 1) + 2 * i + e) + 8) & 15) - 8, 1.f / 16, gc, gs);
      x[e] = (row >> 4) == (ch >> 1) ? gc : (ch >> 1) ? gs : -gs;
    }
    v[i] = pack2(c[0] * 0.125f, c[1] * 0.125f);
    v[4 + i] = pack2(s[0] * 0.125f, s[1] * 0.125f);
    v[8 + i] = pack2(x[0], x[1]);
  }
#pragma unroll
  for (int i = 0; i < 12; i++) asm volatile("" : "+r"(v[i]));
}
__device__ __forceinline__ void fft_tables_store(const uint32_t (&v)[12], uint32_t sb, int tw) {
  const int row = tw >> 2;
  const uint32_t x = ((tw ^ (row >> 1)) & 3) << 4, a = sb + OFF_FT + (16 * (row >> 3) + (row & 7)) * 64 + x;
  sts128(a, v[0], v[1], v[2], v[3]);
  sts128(a + 512, v[4], v[5], v[6], v[7]);
  sts128(sb + OFF_GT + row * 64 + x, v[8], v[9], v[10], v[11]);
}
__device__ __forceinline__ void fft_twiddles(FftConst& k, int w, int lane) {
#pragma unroll
  for (int i = 0; i < 4; i++) {
    float c, s;
    cis((2 * (8 * (i >> 1) + 2 * (lane & 3) + (i & 1)) - 15) * (4 * (8 * w + (lane >> 2)) - 63), 1.f / 4096, c, s);
    k.ta[i] = __fdividef(-s, 1.f + c);
    k.tb[i] = s;
  }
  pin<4>(k.ta);
  pin<4>(k.tb);
}
__device__ __forceinline__ void fft_matrices(FftConst& k, uint32_t sb, int w, int lane) {
  const uint32_t x = (lane >> 1) & 3;
#pragma unroll
  for (int i = 0; i < 2; i++) {
    ldsm4(k.f[i], sb + OFF_FT + (16 * w + (lane & 15)) * 64 + (((2 * i + (lane >> 4)) ^ x) << 4));
    ldsm4t(k.fi[i], sb + OFF_FT + (32 * i + lane) * 64 + ((w ^ x) << 4));
#pragma unroll
    for (int j = 0; j < 4; j++) {
      k.fi[2 + i][j] = (j & 1) ? k.fi[i][j - 1] ^ 0x80008000u : k.fi[i][j + 1];
      asm volatile("" : "+r"(k.fi[2 + i][j]));
    }
  }
}
template <bool INV> __device__ __forceinline__ void rot(float& x, float& y, float a, float b) {
  x = fmaf(INV ? -a : a, y, x);
  y = fmaf(INV ? -b : b, x, y);
  x = fmaf(INV ? -a : a, y, x);
}
__device__ __forceinline__ void twiddle_fwd(uint32_t (&a)[4][4], float* d, const FftConst& k) {
#pragma unroll
  for (int q = 0; q < 4; q++)
#pragma unroll
    for (int j = 0; j < 2; j++) {
      float* x = d + 8 * q + 4 * j;
      rot<false>(x[0], x[2], k.ta[2 * j], k.tb[2 * j]);
      rot<false>(x[1], x[3], k.ta[2 * j + 1], k.tb[2 * j + 1]);
      a[q & 2][2 * j + (q & 1)] = pack2(x[0], x[1]);
      a[(q & 2) + 1][2 * j + (q & 1)] = pack2(x[2], x[3]);
    }
}
__device__ __forceinline__ void g_step(float* d, const uint32_t (&a)[4][4], uint32_t dre, uint32_t dim) {
  WgRS<32>::set<HI_SW64>(d, a[0], dre);
  WgRS<32>::set<HI_SW64>(d + 16, a[2], dre);
  WgRS<32>::mma<HI_SW64>(d, a[1], dim);
  WgRS<32>::mma<HI_SW64>(d + 16, a[3], dim);
  wg_commit();
}

__device__ __forceinline__ void filter_spectra(const FftConst& k, uint32_t sb, int w, int lane) {
  const uint32_t dg = desc_lo(sb + OFF_GT, 16);
  float X[32], H[32];
  uint32_t a[4][4];
  wg_fence();
  WgRS<64>::set<HI_SW32>(X, k.f[0], desc_lo(sb + off_ch(HORD(0)) + U_BYTES, 1024));
  WgRS<64>::mma<HI_SW32>(X, k.f[1], desc_lo(sb + off_ch(HORD(0)) + U_BYTES, 1024) + 32);
  wg_commit();
#pragma unroll 1
  for (int i = 0; i < 5; i++) {
    const int c = HORD(i), cn = HORD(i < 4 ? i + 1 : 4);
    const uint32_t dn = desc_lo(sb + off_ch(cn) + U_BYTES, 1024), ha = sb + off_ch(c) + U_BYTES + 1024 * w + 16 * lane;
    const float dv = __uint_as_float(lds32(sb + OFF_D + 4 * c));
    wg_wait<0>();
    pin<32>(X);
    twiddle_fwd(a, X, k);
    wg_fence();
    g_step(H, a, dg, dg + 64);
    WgRS<64>::set<HI_SW32>(X, k.f[0], dn);
    WgRS<64>::mma<HI_SW32>(X, k.f[1], dn + 32);
    wg_commit();
    wg_sync(3);
    wg_wait<1>();
    pin<32>(H);
#pragma unroll
    for (int j = 0; j < 4; j++) H[4 * (j >> 1) + (j & 1)] += dv;
#pragma unroll
    for (int j = 0; j < 4; j++)
      sts128(ha + 512 * (j & 1) + 4096 * (j >> 1), pack2(H[8 * j], H[8 * j + 1]), pack2(H[8 * j + 2], H[8 * j + 3]),
             pack2(H[8 * j + 4], H[8 * j + 5]), pack2(H[8 * j + 6], H[8 * j + 7]));
    __syncwarp();
    if (lane == 0) mbar_arrive(sb + OFF_BAR + 8 * (B_H + c));
    TSIF(w == 0, 94 + c);
  }
  wg_wait<0>();
}

__device__ __forceinline__ void conv_channel(const FftConst& k, uint32_t sb, int c, int wg, int w, int lane) {
  const uint32_t cb = sb + off_ch(c), bars = sb + OFF_BAR;
  const uint32_t du = desc_lo(cb, 1024), dg = desc_lo(sb + OFF_GT, 16), dz = desc_lo(cb + U_BYTES, 16);
  float U[32], H[32];
  uint32_t a[4][4], e[4][4];
  mbar_wait(bars + 8 * (B_U + (c < 3 ? c : 3)), 0);
  TSM(w == 0 && c < 3, 7 + wg);
  wg_fence();
  WgRS<64>::set<HI_SW32>(U, k.f[0], du);
  WgRS<64>::mma<HI_SW32>(U, k.f[1], du + 32);
  wg_commit();
  mbar_wait(bars + 8 * (B_H + c), 0);
  uint4 hp[4];
#pragma unroll
  for (int j = 0; j < 4; j++) hp[j] = lds128(cb + U_BYTES + 1024 * w + 16 * lane + 512 * (j & 1) + 4096 * (j >> 1));
  wg_wait<0>();
  pin<32>(U);
  twiddle_fwd(e, U, k);
  wg_fence();
  g_step(U, e, dg, dg + 64);
#pragma unroll
  for (int j = 0; j < 4; j++) {
    H[8 * j] = bf_lo(hp[j].x); H[8 * j + 1] = bf_hi(hp[j].x); H[8 * j + 2] = bf_lo(hp[j].y); H[8 * j + 3] = bf_hi(hp[j].y);
    H[8 * j + 4] = bf_lo(hp[j].z); H[8 * j + 5] = bf_hi(hp[j].z); H[8 * j + 6] = bf_lo(hp[j].w); H[8 * j + 7] = bf_hi(hp[j].w);
  }
  if (H_PIN) pin<32>(H);
  wg_wait<0>();
  pin<32>(U);
#pragma unroll
  for (int j = 0; j < 2; j++) {
    float pr[4][2], pi[4][2];
#pragma unroll
    for (int x = 0; x < 2; x++) {
#pragma unroll
      for (int m = 0; m < 4; m++) {
#pragma unroll
        for (int q = 0; q <= m; q++) {
          const int ih = 16 * (q >> 1) + 2 * (q & 1) + 4 * j + x, iu = 16 * ((m - q) >> 1) + 2 * ((m - q) & 1) + 4 * j + x;
          pr[m][x] = q ? fmaf(H[ih], U[iu], pr[m][x]) : H[ih] * U[iu];
          pi[m][x] = q ? fmaf(H[ih], U[iu + 8], pi[m][x]) : H[ih] * U[iu + 8];
          pr[m][x] = fmaf(-H[ih + 8], U[iu + 8], pr[m][x]);
          pi[m][x] = fmaf(H[ih + 8], U[iu], pi[m][x]);
        }
      }
    }
#pragma unroll
    for (int m = 0; m < 4; m++) {
      a[m & 2][2 * j + (m & 1)] = pack2(pr[m][0], pr[m][1]);
      a[(m & 2) + 1][2 * j + (m & 1)] = pack2(pi[m][0], pi[m][1]);
    }
  }
  wg_fence();
  g_step(U, a, dg + 64, dg);
  const uint32_t za = cb + U_BYTES + (8 * w + (lane & 7)) * 128 + (((lane >> 3) ^ (lane & 7)) << 4);
  const uint32_t ya = cb + (lane >> 4) * 1024 + (8 * w + (lane & 7)) * 32 + ((((lane >> 3) ^ (lane >> 2)) & 1) << 4);
  wg_wait<0>();
  pin<32>(U);
  TSIF(w == 0, 80 + c);
#pragma unroll
  for (int p = 0; p < 2; p++) {
#pragma unroll
    for (int i = 0; i < 4; i++) {
      const int j = i & 1;
      float* x = U + 16 * p + 4 * j + (i & 2);
      rot<true>(x[8], x[0], k.ta[2 * j], k.tb[2 * j]);
      rot<true>(x[9], x[1], k.ta[2 * j + 1], k.tb[2 * j + 1]);
      e[p][i] = pack2(x[8], x[9]);
      e[2 + p][i] = pack2(x[0], x[1]);
    }
    stsm4(za ^ (64 * p), e[p]);
    stsm4((za ^ (64 * p)) + 4096, e[2 + p]);
  }
  fence_async_smem();
  wg_sync(1 + wg);
  wg_fence();
  WgRS<64>::set<HI_SW128>(H, k.fi[0], dz);
#pragma unroll
  for (int ks = 1; ks < 4; ks++) WgRS<64>::mma<HI_SW128>(H, k.fi[ks], dz + 128 * ks);
  wg_commit();
  wg_wait<0>();
  pin<32>(H);
  TSIF(w == 0, 88 + c);
#pragma unroll
  for (int j = 0; j < 8; j++)
    a[j >> 2][j & 3] = j < 2 ? pack2(H[4 * j], H[4 * j + 1]) : pack2(H[4 * j] + H[4 * j - 6], H[4 * j + 1] + H[4 * j - 5]);
  stsm4(ya, a[0]);
  stsm4(ya + 2048, a[1]);
  fence_async_smem();
  __syncwarp();
}

__device__ __forceinline__ void prep_slab(uint4* res, const uint2* sw, uint32_t sb, int slab, int w, int lane) {
  const int t = lane & 3, tp = (lane & 7) >> 1, pos = 8 * tp + 2 * (((lane >> 3) + tp) & 3) + (lane & 1);
  const uint32_t base = sb + OFF_KVS + slab * KVS_BYTES + pos * 128;
  uint32_t kk[2][4][4], vv[2][4];
  mbar_wait(sb + OFF_BAR + 8 * (B_KV + slab), 0);
#pragma unroll
  for (int h = 0; h < 2; h++) {
#pragma unroll
    for (int j = 0; j < 4; j++) {
      const uint32_t a = base + 128 * j;
      ldsm4t(kk[h][j], a + (((w + 4 * h) ^ ((a >> 7) & 7)) << 4));
    }
    const uint32_t a = base + KVS_V;
    ldsm4t(vv[h], a + (((w + 4 * h) ^ ((a >> 7) & 7)) << 4));
  }
#pragma unroll
  for (int h = 0; h < 2; h++) {
    uint32_t (&k)[4][4] = kk[h];
    uint32_t (&v)[4] = vv[h];
    const uint32_t w0 = __byte_perm(sw[h].x, 0, 0x1010), w1 = __byte_perm(sw[h].x, 0, 0x3232);
    const uint32_t w2 = __byte_perm(sw[h].y, 0, 0x1010), w3 = __byte_perm(sw[h].y, 0, 0x3232);
#pragma unroll
    for (int m = 0; m < 4; m++)
      v[m] = bmul(badd(badd(badd(bmul(k[0][m], w3), bmul(k[1][m], w2)), bmul(k[2][m], w1)), bmul(k[3][m], w0)), v[m]);
    uint32_t a[4];
#pragma unroll
    for (int m = 0; m < 4; m++) a[m] = (t & 1) ? v[(m + 3) & 3] : v[m];
    res[h] = (t & 2) ? make_uint4(a[2], a[3], a[0], a[1]) : make_uint4(a[0], a[1], a[2], a[3]);
  }
}

__device__ __forceinline__ void prep_gate(const Params& p, int b, int w, int lane) {
  uint2 gw[5], x[4][5];
#pragma unroll
  for (int j = 0; j < 5; j++) gw[j] = ldg64(reinterpret_cast<const uint2*>(p.gate_w) + lane + 32 * j);
#pragma unroll
  for (int i = 0; i < 4; i++)
#pragma unroll
    for (int j = 0; j < 5; j++)
      x[i][j] = ldg64(reinterpret_cast<const uint2*>(p.q) + (16 * b + 4 * w + i) * (DIM / 4) + lane + 32 * j);
  float s[4];
#pragma unroll
  for (int i = 0; i < 4; i++) {
    s[i] = 0.f;
#pragma unroll
    for (int j = 0; j < 5; j++) {
      const uint32_t m0 = bmul(x[i][j].x, gw[j].x), m1 = bmul(x[i][j].y, gw[j].y);
      s[i] += (bf_lo(m0) + bf_hi(m0)) + (bf_lo(m1) + bf_hi(m1));
    }
  }
  const bool h = lane & 16, q = lane & 8;
  const float a = (h ? s[2] : s[0]) + __shfl_xor_sync(0xffffffffu, h ? s[0] : s[2], 16);
  const float c = (h ? s[3] : s[1]) + __shfl_xor_sync(0xffffffffu, h ? s[1] : s[3], 16);
  float z = (q ? c : a) + __shfl_xor_sync(0xffffffffu, q ? a : c, 8);
#pragma unroll
  for (int o = 4; o > 0; o >>= 1) z += __shfl_xor_sync(0xffffffffu, z, o);
  z = bf_lo(pack2(z, 0.f));
  if ((lane & 7) == 0) g_gate[16 * b + 4 * w + (lane >> 3)] = bf_lo(pack2(__fdividef(1.f, 1.f + __expf(-z)), 0.f));
}

__device__ __forceinline__ uint32_t bmax(uint32_t a, uint32_t b) {
  uint32_t d;
  asm("max.bf16x2 %0, %1, %2;" : "=r"(d) : "r"(a), "r"(b));
  return d;
}
__device__ __forceinline__ void softmax_two(const float (&l)[2][2], uint32_t& p0, uint32_t& p1) {
  constexpr float kScale = 0.22360679774997896f, kLog2e = 1.4426950408889634f;
  const uint32_t r0 = pack2(l[0][0], l[1][0]), r1 = pack2(l[0][1], l[1][1]);
  const uint32_t x0 = pack2(bf_lo(r0) * kScale, bf_hi(r0) * kScale), x1 = pack2(bf_lo(r1) * kScale, bf_hi(r1) * kScale);
  uint32_t m = bmax(x0, x1);
  m = bmax(m, __shfl_xor_sync(0xffffffffu, m, 1));
  m = bmax(m, __shfl_xor_sync(0xffffffffu, m, 2));
  const float m0 = bf_lo(m) * kLog2e, m1 = bf_hi(m) * kLog2e;
  p0 = pack2(ex2(bf_lo(x0) * kLog2e - m0), ex2(bf_lo(x1) * kLog2e - m0));
  p1 = pack2(ex2(bf_hi(x0) * kLog2e - m1), ex2(bf_hi(x1) * kLog2e - m1));
}

__device__ __forceinline__ void halo_read(uint32_t (&kpv)[10], uint32_t (&vpv)[10], uint32_t (&tg)[7], const uint4* hp) {
#pragma unroll
  for (int j = 0; j < 7; j++) {
    uint32_t x0, x1, x2;
    asm volatile("ld.relaxed.gpu.global.v4.u32 {%0, %1, %2, %3}, [%4];"
                 : "=r"(x0), "=r"(x1), "=r"(x2), "=r"(tg[j]) : "l"(hp + 32 * j) : "memory");
    if (j < 4) kpv[3 * j] = x0; else vpv[3 * j - 10] = x0;
    if (j < 3) kpv[3 * j + 1] = x1; else vpv[3 * j - 9] = x1;
    if (j < 3) kpv[3 * j + 2] = x2; else if (j < 6) vpv[3 * j - 8] = x2;
  }
}

template <int ROT>
__device__ __forceinline__ void pack_qkv(const float* acc, uint32_t (&qlo)[10], uint32_t (&qhi)[10], uint32_t (&klo)[10],
                                         uint32_t (&khi)[10], uint32_t (&vlo)[10], uint32_t (&vhi)[10]) {
#pragma unroll
  for (int j = 0; j < 10; j++) {
    const int x = (j + ROT) % 10, tq = x < 8 ? x : 16 + x, tk = x < 8 ? 8 + x : 18 + x, tv = x < 8 ? 16 + x : 20 + x;
    khi[j] = pack2(acc[4 * tk + 2], acc[4 * tk + 3]);
    vhi[j] = movm(pack2(acc[4 * tv + 2], acc[4 * tv + 3]));
    qlo[j] = pack2(acc[4 * tq], acc[4 * tq + 1]);
    qhi[j] = pack2(acc[4 * tq + 2], acc[4 * tq + 3]);
    klo[j] = pack2(acc[4 * tk], acc[4 * tk + 1]);
    vlo[j] = pack2(acc[4 * tv], acc[4 * tv + 1]);
    asm volatile("" : "+r"(khi[j]), "+r"(qlo[j]), "+r"(qhi[j]), "+r"(klo[j]), "+r"(vlo[j]));
  }
}

__device__ __forceinline__ void attention(float* acc, uint32_t sb, int b, int par, int w, int lane) {
  const int g = lane >> 2, t = lane & 3;
  uint32_t klo[10], khi[10], vlo[10], vhi[10], qlo[10], qhi[10], kpv[10], vpv[10];
  if (tail_first(b & 7)) pack_qkv<8>(acc, qlo, qhi, klo, khi, vlo, vhi);
  else pack_qkv<0>(acc, qlo, qhi, klo, khi, vlo, vhi);
  uint32_t tag = 0;
  if (w == 0 || w == 3) {
    mbar_wait(sb + OFF_BAR + 8 * B_EPOCH, 0);
    tag = lds32(sb + OFF_EPOCH) + 1;
  }
  const uint32_t xa = sb + OFF_KVX + (par * 3) * 2560 + lane * 16;
  if (w < 3) {
    mbar_wait(sb + OFF_BAR + 8 * B_S3, 0);
    sts128(xa + w * 2560, khi[0], khi[1], khi[2], khi[3]);
    sts128(xa + w * 2560 + 512, khi[4], khi[5], khi[6], khi[7]);
    sts128(xa + w * 2560 + 1024, khi[8], khi[9], vhi[0], vhi[1]);
    sts128(xa + w * 2560 + 1536, vhi[2], vhi[3], vhi[4], vhi[5]);
    sts128(xa + w * 2560 + 2048, vhi[6], vhi[7], vhi[8], vhi[9]);
  } else if (b < NCTA - 8) {
    uint4* ho = g_halo + (b * 2 + par) * 224 + lane;
#pragma unroll
    for (int j = 0; j < 7; j++) {
      const uint32_t x0 = j < 4 ? khi[3 * j] : vhi[3 * j - 10], x1 = j < 3 ? khi[3 * j + 1] : vhi[3 * j - 9];
      const uint32_t x2 = j < 3 ? khi[3 * j + 2] : j < 6 ? vhi[3 * j - 8] : 0u;
      asm volatile("st.relaxed.gpu.global.v4.u32 [%0], {%1, %2, %3, %4};" ::"l"(ho + 32 * j), "r"(x0), "r"(x1), "r"(x2), "r"(tag) : "memory");
    }
  }
  TSIF(par == 0 && w == 1, 64);
  TSIF(par == 0 && w == 3, 76);
#pragma unroll
  for (int j = 0; j < 10; j++) vlo[j] = movm(vlo[j]);
  const bool far0 = 2 * t > g, far1 = 2 * t + 1 > g;
  const uint32_t mfar = (far0 ? 0x0000FFFFu : 0u) | (far1 ? 0xFFFF0000u : 0u);
  float slo[4][2], shi[4][2], lg[2][2];
  uint32_t phi[4], plo[4], qml[4], qmh[4];
#pragma unroll
  for (int h = 0; h < 4; h++) {
    const int f = h == 0 ? 0 : h == 1 ? 3 : h == 2 ? 5 : 8, hf = h < 2 ? 2 : 7;
    const bool mine = (h & 1) ? t >= 2 : t < 2;
    qml[h] = mine ? qlo[hf] : 0u;
    qmh[h] = mine ? qhi[hf] : 0u;
    float a[4] = {0.f, 0.f, 0.f, 0.f}, c[4] = {0.f, 0.f, 0.f, 0.f};
    mma16816(a, qlo[f], qhi[f], qlo[f + 1], qhi[f + 1], klo[f], klo[f + 1]);
    mma16816(c, qlo[f], qhi[f], qlo[f + 1], qhi[f + 1], khi[f], khi[f + 1]);
    mma1688(a, qml[h], qmh[h], klo[hf]);
    mma1688(c, qml[h], qmh[h], khi[hf]);
    slo[h][0] = a[0];
    slo[h][1] = a[1];
    shi[h][0] = lg[h & 1][0] = far0 ? a[2] : c[2];
    shi[h][1] = lg[h & 1][1] = far1 ? a[3] : c[3];
    if (!ATT_MERGE && (h & 1)) softmax_two(lg, phi[h - 1], phi[h]);
  }
  TSIF(par == 0 && w == 1, 65);
  wg_sync(1 + par);
  TSIF(par == 0 && w == 1, 66);
  const bool nohist = (w == 0) && (b < 8);
  const uint4* hp = g_halo + ((b - 8) * 2 + par) * 224 + lane;
  uint32_t tg[7];
  if (w > 0) {
    const uint4 v0 = lds128(xa + (w - 1) * 2560), v1 = lds128(xa + (w - 1) * 2560 + 512), v2 = lds128(xa + (w - 1) * 2560 + 1024);
    const uint4 v3 = lds128(xa + (w - 1) * 2560 + 1536), v4 = lds128(xa + (w - 1) * 2560 + 2048);
    kpv[0] = v0.x; kpv[1] = v0.y; kpv[2] = v0.z; kpv[3] = v0.w; kpv[4] = v1.x; kpv[5] = v1.y; kpv[6] = v1.z; kpv[7] = v1.w;
    kpv[8] = v2.x; kpv[9] = v2.y; vpv[0] = v2.z; vpv[1] = v2.w; vpv[2] = v3.x; vpv[3] = v3.y; vpv[4] = v3.z; vpv[5] = v3.w;
    vpv[6] = v4.x; vpv[7] = v4.y; vpv[8] = v4.z; vpv[9] = v4.w;
  } else if (nohist) {
#pragma unroll
    for (int j = 0; j < 10; j++) kpv[j] = vpv[j] = 0u;
  } else {
    TSIF(par == 0, 77);
    halo_read(kpv, vpv, tg, hp);
  }
  if (w == 0 && !nohist) {
    int spins = 0;
    while (true) {
      bool ok = true;
#pragma unroll
      for (int j = 0; j < 7; j++) ok = ok && tg[j] == tag;
      if (__all_sync(0xffffffffu, ok) || ++spins > SPIN_LIMIT) break;
      halo_read(kpv, vpv, tg, hp);
    }
    TSIF(par == 0, 79);
  }
#pragma unroll
  for (int h = 0; h < 4; h++) {
    const int f = h == 0 ? 0 : h == 1 ? 3 : h == 2 ? 5 : 8, hf = h < 2 ? 2 : 7;
    float a[4] = {0.f, 0.f, 0.f, 0.f};
    mma16816(a, qlo[f], qhi[f], qlo[f + 1], qhi[f + 1], kpv[f], kpv[f + 1]);
    mma1688(a, qml[h], qmh[h], kpv[hf]);
    const float ninf = __int_as_float(0xff800000);
    lg[h & 1][0] = far0 ? (nohist ? ninf : a[0]) : slo[h][0];
    lg[h & 1][1] = far1 ? (nohist ? ninf : a[1]) : slo[h][1];
    if (h & 1) {
      softmax_two(lg, plo[h - 1], plo[h]);
      if (ATT_MERGE) {
        const float lh[2][2] = {{shi[h - 1][0], shi[h - 1][1]}, {shi[h][0], shi[h][1]}};
        softmax_two(lh, phi[h - 1], phi[h]);
      }
    }
  }
  TSIF(par == 0 && w <= 1, 67 + w);
  uint32_t ov[20];
#pragma unroll
  for (int hp = 0; hp < 2; hp++) {
    const int hf = hp ? 7 : 2;
    float sh[4] = {0.f, 0.f, 0.f, 0.f}, i0 = 0.f, i1 = 0.f;
#pragma unroll
    for (int e = 0; e < 2; e++) {
      const int h = 2 * hp + e, f = h == 0 ? 0 : h == 1 ? 3 : h == 2 ? 5 : 8;
      const uint32_t a0 = plo[h] & mfar, a2 = plo[h] & ~mfar, a3 = phi[h] & mfar, c1 = phi[h] & ~mfar;
      float sum[4] = {0.f, 0.f, 0.f, 0.f};
      mma1688(sum, plo[h], phi[h], 0x3F803F80u);
      const float r0 = rcp(sum[0]), r1 = rcp(sum[2]);
#pragma unroll
      for (int j = f; j < f + 2; j++) {
        float o[4] = {0.f, 0.f, 0.f, 0.f};
        mma16816(o, a0, 0u, a2, a3, vpv[j], vlo[j]);
        mma1688(o, 0u, c1, vhi[j]);
        ov[2 * j] = pack2(o[0] * r0, o[1] * r0);
        ov[2 * j + 1] = pack2(o[2] * r1, o[3] * r1);
      }
      const bool mine = e ? g >= 4 : g < 4;
      mma16816(sh, a0, 0u, a2, a3, mine ? vpv[hf] : 0u, mine ? vlo[hf] : 0u);
      mma1688(sh, 0u, c1, mine ? vhi[hf] : 0u);
      if (e == 0 || t >= 2) {
        i0 = r0;
        i1 = r1;
      }
    }
    ov[2 * hf] = pack2(sh[0] * i0, sh[1] * i0);
    ov[2 * hf + 1] = pack2(sh[2] * i1, sh[3] * i1);
  }
  TS(32 + 4 * par + w);
  mbar_wait(sb + OFF_BAR + 8 * B_P1, 0);
  const uint32_t oa = sb + OFF_OA + (lane >> 4) * 2048 + (32 * w + 2 * (lane & 15) + par) * 16;
#pragma unroll
  for (int j = 0; j < 5; j++) stsm4(oa + 4096 * j, ov + 4 * j);
  TSIF(par == 0 && w == 0, 120);
  fence_async_smem();
  TSIF(par == 0 && w == 0, 121);
  __syncwarp();
  if (lane == 0) mbar_arrive(sb + OFF_BAR + 8 * B_ATTN);
  TSIF(par == 0 && w == 0, 122);
}

struct Maps {
  CUtensorMap x, wm, wt, k, v, y, wo, qm, qt, om, ot;
};

__device__ __forceinline__ void load_stage(uint32_t sb, int kb, int b, const Maps& m) {
  const uint32_t st = sb + (kb & 3) * STAGE_BYTES, bar = sb + OFF_BAR + 8 * (B_FULL1 + (kb & 3));
  const int r = b >> 3, hg = b & 7, slab = kb - KV_KB;
  const bool kv = slab >= 0 && slab < 5;
  const uint32_t kbar = sb + OFF_BAR + 8 * (B_KV + slab), dst = sb + OFF_KVS + slab * KVS_BYTES;
  mbar_expect_tx(bar, STAGE_BYTES);
  if (kv) mbar_expect_tx(kbar, KVS_BYTES);
  tma_3d(st, &m.x, 64 * kb, 64 * r, 0, bar);
  if (kv && KV_MIX) tma_3d(dst, &m.k, 0, 32 * (b >> 1) - 3, 2 * slab + (b & 1), kbar);
  tma_3d(st + ST_W, &m.wm, 80 * hg + (tail_first(hg) ? 16 : 0), 64 * kb, 0, bar);
  if (kv && KV_MIX) tma_3d(dst + KVS_V, &m.v, 0, 32 * (b >> 1), 2 * slab + (b & 1), kbar);
  tma_3d(st + ST_WT, &m.wt, 80 * hg + (tail_first(hg) ? 0 : 64), 64 * kb, 0, bar);
  if (kv && !KV_MIX) tma_3d(dst, &m.k, 0, 32 * (b >> 1) - 3, 2 * slab + (b & 1), kbar);
  if (kv && !KV_MIX) tma_3d(dst + KVS_V, &m.v, 0, 32 * (b >> 1), 2 * slab + (b & 1), kbar);
}

__global__ void __launch_bounds__(NTHR, 1) fused_kernel(const __grid_constant__ Maps m, const Params p) {
  extern __shared__ __align__(1024) uint8_t smem[];
  const uint32_t sb = (uint32_t)__cvta_generic_to_shared(smem);
  const uint32_t bars = sb + OFF_BAR;
  const int tid = threadIdx.x, lane = tid & 31;
  int b = blockIdx.x;
  if (BMAP == 1) b = (((b & 63) >> 3) * 2 + (b & 1)) * 8 + (((b < 64 ? 0x6521 : 0x7430) >> (4 * ((b >> 1) & 3))) & 7);
  if (BMAP == 2) b = ((b & 63) >> 2) * 8 + (((b < 64 ? 0x6521 : 0x7430) >> (4 * (b & 3))) & 7);
  if (BMAP == 3) b = (((b & 63) >> 3) * 2 + (b & 1)) * 8 + (((b < 64 ? 0x7430 : 0x6521) >> (4 * ((b >> 1) & 3))) & 7);
  if (BMAP == 4) b = (((b >> 4) * 2 + (b & 1)) * 8) + ((b >> 1) & 7);
  if (BMAP == 5) b = 127 - b;
  const int r = b >> 3, hg = b & 7;

  if (tid == T_ISSUE) {
    TSM(true, 0);
#pragma unroll
    for (int i = 0; i < 4; i++) mbar_init(bars + 8 * (B_FULL1 + i), 1);
#pragma unroll
    for (int i = 0; i < 3; i++) mbar_init(bars + 8 * (B_KV + i), 1);
    fence_async_smem();
#pragma unroll 1
    for (int kb = 0; kb <= PRE2; kb++) load_stage(sb, kb, b, m);
  } else if (tid >= T_PF && tid < T_PF + 11) {
    tm_prefetch(&m.x + (tid - T_PF));
  } else if (tid == T_INIT) {
#pragma unroll
    for (int i = 0; i < 4; i++) mbar_init(bars + 8 * (B_EMPTY1 + i), 8);
#pragma unroll
    for (int i = 0; i < 8; i++) mbar_init(bars + 8 * (B_FULL2 + i), 1);
#pragma unroll
    for (int i = 0; i < 4; i++) mbar_init(bars + 8 * (B_EMPTY2 + i), 8);
#pragma unroll
    for (int i = 0; i < 4; i++) mbar_init(bars + 8 * (B_U + i), 1);
    mbar_init(bars + 8 * B_HA, 4);
    mbar_init(bars + 8 * B_GATE, 4);
    mbar_init(bars + 8 * B_HB, 1);
    mbar_init(bars + 8 * B_KVD, 4);
    mbar_init(bars + 8 * B_QF, 1);
    mbar_init(bars + 8 * B_ATTN, 8);
    mbar_init(bars + 8 * B_P1, 8);
    mbar_init(bars + 8 * B_C34, 1);
#pragma unroll
    for (int i = 0; i < 5; i++) mbar_init(bars + 8 * (B_YST + i), 4);
#pragma unroll
    for (int i = 0; i < 5; i++) mbar_init(bars + 8 * (B_H + i), 4);
    mbar_init(bars + 8 * B_YSIG, 1);
    mbar_init(bars + 8 * B_YFULL, 1);
    mbar_init(bars + 8 * B_EPOCH, 1);
    mbar_init(bars + 8 * B_PREP, 4);
    mbar_init(bars + 8 * B_USIG, 1);
    mbar_init(bars + 8 * B_WST, 1);
#pragma unroll
    for (int i = 3; i < 5; i++) mbar_init(bars + 8 * (B_KV + i), 1);
    mbar_init(bars + 8 * B_E3, 8);
    mbar_init(bars + 8 * B_LAST, 1);
    mbar_init(bars + 8 * B_OSIG, 1);
    mbar_init(bars + 8 * B_WOP, 1);
    fence_async_smem();
  }
  const int warp = __shfl_sync(0xffffffffu, tid >> 5, 0), wg = warp >> 2, w = warp & 3;
  __syncthreads();

  if (wg == 3) {
    asm volatile("setmaxnreg.dec.sync.aligned.u32 56;");
    if (w == 0) {
      if (lane == 0) {
#pragma unroll 1
        for (int kb = 1 + PRE2; kb < 10; kb++) {
          if (kb >= 4) mbar_wait(bars + 8 * (kb == 7 ? B_E3 : B_EMPTY1 + (kb & 3)), (kb >> 3) & 1);
          TSIF(kb >= 4, 44 + kb);
          load_stage(sb, kb, b, m);
          if (kb == TRIG_KB) mbar_arrive(bars + 8 * B_LAST);
        }
        mbar_wait(bars + 8 * B_WOP, 0);
        mbar_wait(bars + 8 * B_P1, 0);
        mbar_wait(bars + 8 * WL_TRIG, 0);
        mbar_wait(bars + 8 * B_EPOCH, 0);
        flag_wait(g_cnt + C_W + 32 * hg, (lds32(sb + OFF_EPOCH) + 1) * 16);
        TS(30);
#pragma unroll 1
        for (int j = 0; j < 8; j++) {
          if (j >= 6) mbar_wait(bars + 8 * (B_EMPTY2 + j - 6), 0);
          if (j == 4) mbar_wait(bars + 8 * B_ATTN, 0);
          TSIF(j >= 6, 100 + j);
          if (RF_GATE && j == 6) mbar_wait(bars + 8 * B_YSIG, 0);
          mbar_expect_tx(bars + 8 * (B_FULL2 + j), j == 0 ? WO_BYTES : j == 5 ? O_BYTES + WO_BYTES + 512 : O_BYTES + WO_BYTES);
          bulk_load(sb + off_w(j), g_WO + (hg * 8 + step_src(hg, j)) * 800, WO_BYTES, bars + 8 * (B_FULL2 + j));
        }
        mbar_wait(bars + 8 * (B_EMPTY2 + 3), 0);
        mbar_expect_tx(bars + 8 * B_QF, O_BYTES);
        tma_2d(sb + OFF_QS, &m.qm, 80 * hg, 128 * r, bars + 8 * B_QF);
        tma_2d(sb + OFF_QT, &m.qt, 80 * hg + 64, 128 * r, bars + 8 * B_QF);
      }
    } else if (w == 1) {
      unsigned epoch = 0;
      if (lane == 0) {
        epoch = atomicAdd(g_cnt + C_LAUNCH, 1u) / NCTA;
        asm volatile("st.shared.u32 [%0], %1;" ::"r"(sb + OFF_EPOCH), "r"(epoch) : "memory");
        mbar_arrive(bars + 8 * B_EPOCH);
        mbar_wait(bars + 8 * B_KVD, 0);
        mbar_expect_tx(bars + 8 * B_HB, 5 * 4096);
#pragma unroll 1
        for (int c = 0; c < 5; c++) {
          if (c == 3) mbar_wait(bars + 8 * B_S3, 0);
          bulk_load(sb + off_ch(c) + U_BYTES, p.ssm_k + (5 * b + c) * SEQ, 4096, bars + 8 * B_HB);
        }
#pragma unroll
        for (int c = 0; c < 4; c++) mbar_expect_tx(bars + 8 * (B_U + c), c < 3 ? U_BYTES : 2 * U_BYTES);
        const uint4* usrc = g_U + 5 * b * U_PITCH;
        mbar_wait(bars + 8 * B_USIG, 0);
        flag_wait(g_cnt + C_PREP + 32 * (b & 15), (epoch + 1) * NCTA);
        TS(23);
#pragma unroll
        for (int c = 0; c < 5; c++) {
          if (c == 3) mbar_wait(bars + 8 * (B_U + 2), 0);
          bulk_load(sb + off_ch(c), usrc + c * U_PITCH, U_BYTES, bars + 8 * (B_U + (c < 3 ? c : 3)));
          TSIF(c == 0 || c == 4, 116 + (c >> 2));
        }
      }
      epoch = __shfl_sync(0xffffffffu, epoch, 0);
      if (lane < 8) {
        const int src = (b & ~7) | step_src(hg, lane);
        mbar_wait(bars + 8 * B_OSIG, 0);
        TS(20);
        flag_wait(g_cnt + C_O + 32 * src, epoch + 1);
        if (lane >= 1 && lane < 4) bulk_load(sb + off_o(lane), g_O + src * 1280, O_BYTES, bars + 8 * (B_FULL2 + lane));
        __syncwarp(0xff);
        TS(21);
        if (lane == 5) bulk_load(sb + OFF_GATE, g_gate + 128 * r, 512, bars + 8 * (B_FULL2 + 5));
#pragma unroll 1
        for (int j = 4; j < 8; j++) {
          if (lane == j) {
            mbar_wait(bars + 8 * (j < 6 ? B_C34 : B_EMPTY2 + j - 6), 0);
            if (RF_GATE && j == 6) mbar_wait(bars + 8 * B_YSIG, 0);
            bulk_load(sb + off_o(j), g_O + src * 1280, O_BYTES, bars + 8 * (B_FULL2 + j));
          }
          __syncwarp(0xff);
        }
        TS(22);
      }
    } else if (w == 2) {
      mbar_wait(bars + 8 * B_PREP, 0);
      flag_signal(g_cnt + C_PREP, 16, lane);
      TS(25);
      if (lane == 0) mbar_arrive(bars + 8 * B_USIG);
      mbar_wait(bars + 8 * B_GATE, 0);
      if ((NOMB & 1) && lane == 0) asm volatile("fence.release.gpu;" ::: "memory");
      mbar_wait(bars + 8 * B_ATTN, 0);
      if (lane == 0) {
        if (O_DEFER) mbar_wait(bars + 8 * (B_U + 3), 0);
        asm volatile("cp.async.bulk.global.shared::cta.bulk_group [%0], [%1], 20480;\ncp.async.bulk.commit_group;\n"
                     "cp.async.bulk.wait_group 0;\nfence.proxy.async.global;" ::"l"(g_O + b * 1280), "r"(sb + OFF_OA) : "memory");
      }
      TS(74);
      if (!(NOMB & 1)) flag_signal(g_cnt + C_O + 32 * b, 1, lane);
      else if (lane == 0) flag_bump(g_cnt + C_O + 32 * b);
      TS(26);
      if (lane == 0) mbar_arrive(bars + 8 * B_OSIG);

    } else {
      if (lane == 0) {
        uint4* dst = g_WO + (hg * 8 + (r >> 1)) * 800 + (r & 1) * 80;
        mbar_wait(bars + 8 * B_P1, 0);
        mbar_wait(bars + 8 * WB_TRIG, 0);
        mbar_expect_tx(bars + 8 * B_WST, WO_BYTES / 2);
        tma_3d(sb + OFF_WS, &m.wo, 0, 40 * r, 5 * hg, bars + 8 * B_WST);
        mbar_wait(bars + 8 * B_WST, 0);
        mbar_wait(bars + 8 * WO_TRIG, 0);
#pragma unroll 1
        for (int n = 0; n < 5; n++)
          asm volatile("cp.async.bulk.global.shared::cta.bulk_group [%0], [%1], 1280;" ::"l"(dst + 160 * n), "r"(sb + OFF_WS + 1280 * n) : "memory");
        asm volatile("cp.async.bulk.commit_group;\ncp.async.bulk.wait_group 0;\nfence.proxy.async.global;" ::: "memory");
        if (!(NOMB & 4)) asm volatile("fence.release.gpu;" ::: "memory");
        flag_bump(g_cnt + C_W + 32 * hg);
        mbar_arrive(bars + 8 * B_WOP);
        TS(71);
#pragma unroll 1
        for (int c = 0; c < 5; c++) {
          mbar_wait(bars + 8 * (B_YST + c), 0);
          asm volatile("cp.async.bulk.global.shared::cta.bulk_group [%0], [%1], 4096;\ncp.async.bulk.commit_group;"
                       ::"l"(g_Y + (5 * b + c) * Y_PITCH), "r"(sb + off_ch(c)) : "memory");
          if (c == 2) {
            asm volatile("cp.async.bulk.wait_group.read 0;" ::: "memory");
            mbar_arrive(bars + 8 * B_C34);
          }
        }
        asm volatile("cp.async.bulk.wait_group 0;\nfence.proxy.async.global;" ::: "memory");
        TS(75);
        if (!(NOMB & 2)) asm volatile("fence.release.gpu;" ::: "memory");
        flag_bump(g_cnt + C_Y + 32 * (b >> 4));
        TS(27);
        mbar_arrive(bars + 8 * B_YSIG);
        mbar_expect_tx(bars + 8 * B_YFULL, 20480);
        flag_wait(g_cnt + C_Y + 32 * hg, (lds32(sb + OFF_EPOCH) + 1) * 16);
        TS(24);
        tma_2d(sb + OFF_YT, &m.y, 128 * r, 80 * hg, bars + 8 * B_YFULL);
        tma_2d(sb + OFF_YT + 10240, &m.y, 128 * r + 64, 80 * hg, bars + 8 * B_YFULL);
      }
    }
  } else {
    asm volatile("setmaxnreg.inc.sync.aligned.u32 152;");
    if (wg < 2) {
      float acc[120];
#pragma unroll
      for (int i = 0; i < 120; i++) acc[i] = 0.f;
      const uint32_t da = desc_lo(sb + wg * 8192, 16), db = desc_lo(sb + ST_W, 8192), dc = desc_lo(sb + ST_WT, 2048);
      if (PW1) pin<120>(acc);
      if (PW1 == 2) mbar_wait(bars + 8 * B_FULL1, 0);
#pragma unroll 1
      for (int kb = 0; kb < 10; kb++) {
        mbar_wait(bars + 8 * (B_FULL1 + (kb & 3)), (kb >> 2) & 1);
        const uint32_t so = (kb & 3) * (STAGE_BYTES >> 4);
        wg_fence();
#pragma unroll
        for (int k = 0; k < 4; k++) {
          WgSST<192>::mma<HI_SW128, HI_SW128>(acc, da + so + 2 * k, db + so + 128 * k, 1);
          WgSST<48>::mma<HI_SW128, HI_SW32>(acc + 96, da + so + 2 * k, dc + so + 32 * k, 1);
        }
        wg_commit();
        wg_wait<1>();
        if (kb > 0 && lane == 0) mbar_arrive(bars + 8 * (kb == 4 ? B_E3 : B_EMPTY1 + ((kb - 1) & 3)));
      }
      wg_wait<0>();
      pin<120>(acc);
      if (lane == 0) mbar_arrive(bars + 8 * B_P1);
      TSM(w == 0, 3 + wg);
      attention(acc, sb, b, wg, w, lane);
    } else {
      const int tw = tid & 127, chl = 64 * (b & 1) + 8 * w + (lane >> 2);
      uint4* up = g_U + chl * U_PITCH + ((4 * (b >> 1) + (lane & 3)) ^ ((b >> 2) & 1));
      uint2 sw[10];
      uint32_t dv = 0;
      if (lane < 5) dv = __ldg(reinterpret_cast<const unsigned short*>(p.ssm_D) + 5 * b + lane);
#pragma unroll
      for (int i = 0; i < 10; i++) sw[i] = ldg64(reinterpret_cast<const uint2*>(p.shift_k) + chl + 128 * (i >> 1) + 32 * (i & 1));
      uint32_t tab[12];
      fft_tables(tab, tw);
      uint4 res[10];
#pragma unroll
      for (int i = 0; i < 10; i++) res[i] = make_uint4(0, 0, 0, 0);
#pragma unroll 1
      for (int slab = 0; slab < 5; slab++) {
#pragma unroll
        for (int i = 0; i < 8; i++) res[i] = res[i + 2];
        prep_slab(res + 8, sw, sb, slab, w, lane);
        TSIF(w == 0, 99 + 4 * slab);
#pragma unroll
        for (int i = 0; i < 8; i++) sw[i] = sw[i + 2];
      }
      TSIF(w == 0, 28);
      __syncwarp();
      if (lane == 0) mbar_arrive(bars + 8 * B_KVD + ((res[8].x ^ res[9].x) & p.zero));
      mbar_wait(bars + 8 * B_KVD, 0);
      fft_tables_store(tab, sb, tw);
      mbar_wait(bars + 8 * B_LAST, 0);
#pragma unroll
      for (int i = 0; i < 10; i++) up[(128 * (i >> 1) + 32 * (i & 1)) * U_PITCH] = res[i];
      __syncwarp();
      if (lane == 0) mbar_arrive(bars + 8 * B_PREP);
      TSIF(w == 0, 5);
      mbar_wait(bars + 8 * (G_AFTER ? B_USIG : B_LAST), 0);
      prep_gate(p, b, w, lane);
      __syncwarp();
      if (lane == 0) mbar_arrive(bars + 8 * B_GATE);
      TSIF(w == 0, 72);
      mbar_wait(bars + 8 * B_HB, 0);
      TSIF(w == 0, 123);
      const uint32_t ha = sb + U_BYTES + ((tw >> 3) * 16 + 8 + (tw & 7)) * 16;
      uint4 hv[5];
#pragma unroll
      for (int c = 0; c < 5; c++) hv[c] = lds128(ha + off_ch(c));
      __syncwarp();
#pragma unroll
      for (int c = 0; c < 5; c++) sts128((ha ^ 16) + off_ch(c), hv[c].x, hv[c].y, hv[c].z, hv[c].w);
      if (tw < 5) asm volatile("st.shared.f32 [%0], %1;" ::"r"(sb + OFF_D + 4 * tw), "f"(bf_lo(dv) * 0.125f) : "memory");
      fence_async_smem();
      __syncwarp();
      if (lane == 0) mbar_arrive(bars + 8 * B_HA);
      TSIF(w == 0, 6);
    }

    FftConst fc;
    fft_twiddles(fc, w, lane);
    mbar_wait(bars + 8 * B_HA, 0);
    fft_matrices(fc, sb, w, lane);
    if (wg == 2) filter_spectra(fc, sb, w, lane);
    if (ATT_GATE) mbar_wait(bars + 8 * B_ATTN, 0);
    TSIF(w == 0 && wg == 2, 124);
#pragma unroll 1
    for (int c = wg == 2 ? 0 : wg + 1; c < 5; c += 3) {
      conv_channel(fc, sb, c, wg, w, lane);
      if (lane == 0) mbar_arrive(bars + 8 * (B_YST + c));
      TSM(w == 0, 10 + c);
    }

    if (wg < 2) {
      const int g = lane >> 2;
      float acc[40];
#pragma unroll
      for (int i = 0; i < 40; i++) acc[i] = 0.f;
      const uint32_t da = desc_lo(sb + wg * 1024, 2048), db = desc_lo(sb, 2560);
      mbar_wait(bars + 8 * B_ATTN, 0);
      mbar_wait(bars + 8 * (B_YST + 3), 0);
      mbar_wait(bars + 8 * (B_YST + 4), 0);
      if (PW2) mbar_wait(bars + 8 * B_FULL2, 0);
#pragma unroll 1
      for (int j = 0; j < 8; j++) {
        mbar_wait(bars + 8 * (B_FULL2 + j), 0);
        const uint32_t oa = da + (off_o(j) >> 4), ob = db + (off_w(j) >> 4);
        wg_fence();
#pragma unroll
        for (int k = 0; k < 5; k++) WgSST<80>::mma<HI_NONE, HI_SW32>(acc, oa + 256 * k, ob + 32 * k, 1);
        wg_commit();
        wg_wait<1>();
        if (j >= 1 && j <= 4 && lane == 0) mbar_arrive(bars + 8 * (B_EMPTY2 + j - 1));
      }
      TSIF(w == 0 && wg == 0, 113);
      const int tr = 64 * wg + 16 * w + (lane & 15);
      const uint32_t fm = sb + OFF_QS + tr * 128, fx = (lane >> 4) ^ (tr & 7);
      const uint32_t ft = sb + OFF_QT + tr * 32 + (((lane >> 4) ^ (tr >> 2)) & 1) * 16;
      const float g0 = __uint_as_float(lds32(sb + OFF_GATE + (64 * wg + 16 * w + g) * 4));
      const float g1 = __uint_as_float(lds32(sb + OFF_GATE + (64 * wg + 16 * w + 8 + g) * 4));
      const uint32_t ga = pack2(g0, g0), gb = pack2(g1, g1);
      const uint32_t na = pack2(1.f - g0, 1.f - g0), nb = pack2(1.f - g1, 1.f - g1);

      wg_wait<0>();
      pin<40>(acc);
      TSM(w == 0, 17 + wg);
      uint32_t pb[20];
#pragma unroll
      for (int j = 0; j < 10; j++) {
        pb[2 * j] = bmul(na, pack2(acc[4 * j], acc[4 * j + 1]));
        pb[2 * j + 1] = bmul(nb, pack2(acc[4 * j + 2], acc[4 * j + 3]));
        asm volatile("" : "+r"(pb[2 * j]), "+r"(pb[2 * j + 1]));
      }
      const uint32_t ya = sb + OFF_YT + wg * 10240 + ((lane >> 4) * 8 + (lane & 7)) * 128 +
                          (((2 * w + (((lane >> 3) & 1) ^ wg)) ^ (lane & 7)) << 4);
      uint32_t qf[20];
      mbar_wait(bars + 8 * B_QF, 0);
#pragma unroll
      for (int j = 0; j < 5; j++) ldsm4(qf + 4 * j, j < 4 ? fm + ((fx ^ (2 * j)) << 4) : ft);
      mbar_wait(bars + 8 * B_YFULL, 0);
      TSIF(w == 0 && wg == 0, 19);
#pragma unroll
      for (int j = 0; j < 5; j++) {
        uint32_t y[4];
        ldsm4t(y, ya + 2048 * j);
#pragma unroll
        for (int i = 0; i < 4; i++) qf[4 * j + i] = badd(bmul((i & 1) ? gb : ga, bmul(qf[4 * j + i], y[i])), pb[4 * j + i]);
      }
#pragma unroll
      for (int j = 0; j < 5; j++) stsm4(j < 4 ? fm + ((fx ^ (2 * j)) << 4) : ft, qf + 4 * j);
      fence_async_smem();
      __syncwarp();
      if (lane == 0) {
        const int row = 64 * wg + 16 * w;
        asm volatile("cp.async.bulk.tensor.2d.global.shared::cta.bulk_group [%0, {%2, %3}], [%1];"
                     ::"l"(&m.om), "r"(sb + OFF_QS + row * 128), "r"(80 * hg), "r"(128 * r + row) : "memory");
        asm volatile("cp.async.bulk.tensor.2d.global.shared::cta.bulk_group [%0, {%2, %3}], [%1];"
                     ::"l"(&m.ot), "r"(sb + OFF_QT + row * 32), "r"(80 * hg + 64), "r"(128 * r + row) : "memory");
        asm volatile("cp.async.bulk.commit_group;\ncp.async.bulk.wait_group.read 0;" ::: "memory");
      }
      TSM(true, 40 + 4 * wg + w);
      if (ENDBAR) asm volatile("bar.sync 15, 256;" ::: "memory");
    }
  }
}

typedef CUresult (*EncodeFn)(CUtensorMap*, CUtensorMapDataType, cuuint32_t, void*, const cuuint64_t*, const cuuint64_t*,
                             const cuuint32_t*, const cuuint32_t*, CUtensorMapInterleave, CUtensorMapSwizzle,
                             CUtensorMapL2promotion, CUtensorMapFloatOOBfill);

void encode(EncodeFn fn, CUtensorMap* tm, const void* base, int rank, const cuuint64_t* dims, const cuuint64_t* strides,
            const cuuint32_t* box, CUtensorMapSwizzle swz) {
  const cuuint32_t ones[3] = {1, 1, 1};
  fn(tm, CU_TENSOR_MAP_DATA_TYPE_BFLOAT16, rank, const_cast<void*>(base), dims, strides, box, ones,
     CU_TENSOR_MAP_INTERLEAVE_NONE, swz, CU_TENSOR_MAP_L2_PROMOTION_L2_128B, CU_TENSOR_MAP_FLOAT_OOB_FILL_NONE);
}

}

extern "C" void kernel_launch(void* const* d_in, const int* in_sizes, int n_in, void* d_out, int out_size) {
  (void)in_sizes; (void)n_in; (void)out_size;
  Params p;
  p.q = (const __nv_bfloat16*)d_in[0];
  p.k = (const __nv_bfloat16*)d_in[1];
  p.v = (const __nv_bfloat16*)d_in[2];
  p.shift_k = (const __nv_bfloat16*)d_in[3];
  p.ssm_k = (const __nv_bfloat16*)d_in[4];
  p.ssm_D = (const __nv_bfloat16*)d_in[5];
  p.wqkv = (const __nv_bfloat16*)d_in[7];
  p.wo = (const __nv_bfloat16*)d_in[8];
  p.gate_w = (const __nv_bfloat16*)d_in[9];
  p.out = (__nv_bfloat16*)d_out;
  p.zero = 0;

  static EncodeFn fn = nullptr;
  static void* yaddr = nullptr;
  if (!fn) {
    cudaDriverEntryPointQueryResult qr;
    void* f = nullptr;
    cudaGetDriverEntryPoint("cuTensorMapEncodeTiled", &f, cudaEnableDefault, &qr);
    fn = (EncodeFn)f;
    cudaGetSymbolAddress(&yaddr, g_Y);
    cudaFuncSetAttribute(fused_kernel, cudaFuncAttributeMaxDynamicSharedMemorySize, SMEM_BYTES);
  }
  Maps m;
  {
    const cuuint64_t dims[3] = {640, 1024, 2}, st[2] = {2560, 1280};
    const cuuint32_t box[3] = {64, 64, 2};
    encode(fn, &m.x, p.q, 3, dims, st, box, CU_TENSOR_MAP_SWIZZLE_128B);
  }
  {
    const cuuint64_t dims[3] = {640, 640, 3}, st[2] = {3840, 1280};
    const cuuint32_t box[3] = {64, 64, 3}, boxt[3] = {16, 64, 3};
    encode(fn, &m.wm, p.wqkv, 3, dims, st, box, CU_TENSOR_MAP_SWIZZLE_128B);
    encode(fn, &m.wt, p.wqkv, 3, dims, st, boxt, CU_TENSOR_MAP_SWIZZLE_32B);
  }
  {
    const cuuint64_t dims[3] = {64, 2048, 10}, st[2] = {1280, 128};
    const cuuint32_t boxk[3] = {64, 35, 1}, boxv[3] = {64, 32, 1};
    encode(fn, &m.k, p.k, 3, dims, st, boxk, CU_TENSOR_MAP_SWIZZLE_128B);
    encode(fn, &m.v, p.v, 3, dims, st, boxv, CU_TENSOR_MAP_SWIZZLE_128B);
  }
  {
    const cuuint64_t dims[3] = {16, 640, 40}, st[2] = {1280, 32};
    const cuuint32_t box[3] = {16, 40, 5};
    encode(fn, &m.wo, p.wo, 3, dims, st, box, CU_TENSOR_MAP_SWIZZLE_32B);
  }
  {
    const cuuint64_t dims[2] = {2048, 640}, st[1] = {Y_PITCH * 16};
    const cuuint32_t box[2] = {64, 80};
    encode(fn, &m.y, yaddr, 2, dims, st, box, CU_TENSOR_MAP_SWIZZLE_128B);
  }
  {
    const cuuint64_t dims[2] = {640, 2048}, st[1] = {1280};
    const cuuint32_t bqm[2] = {64, 128}, bqt[2] = {16, 128}, bom[2] = {64, 16}, bot[2] = {16, 16};
    encode(fn, &m.qm, p.q, 2, dims, st, bqm, CU_TENSOR_MAP_SWIZZLE_128B);
    encode(fn, &m.qt, p.q, 2, dims, st, bqt, CU_TENSOR_MAP_SWIZZLE_32B);
    encode(fn, &m.om, p.out, 2, dims, st, bom, CU_TENSOR_MAP_SWIZZLE_128B);
    encode(fn, &m.ot, p.out, 2, dims, st, bot, CU_TENSOR_MAP_SWIZZLE_32B);
  }
  fused_kernel<<<NCTA, NTHR, SMEM_BYTES>>>(m, p);
}
```

```cpp
#include <cuda.h>
#include <cuda_bf16.h>
#include <cuda_runtime.h>
#include <stdint.h>

namespace {

constexpr int SEQ = 2048, DIM = 640, NCTA = 128, NTHR = 512;

#define TRIG_KB 9
#define KV_KB 2
#define DEV_EXIT 0
#define ATT_GATE 1
#define G_AFTER 0
#define FENCE_LO 0
#define FENCE_HI 0
#define PW1 2
#define PW2 1
#define ENDBAR 0
#define PAD_KB 0
#define Y_ALIAS 1
#define H_EARLY 1
#define NOMB 0
#define SRC_ROT 0
#define WAIT_NS 0
#define WB_TRIG B_USIG
#define G_POS 0
#define TAILF 1
#define T_ISSUE 384
#define T_PF 416
#define T_INIT 448
#define ATT_MERGE 0
#define BMAP 1
#define PRE2 1
#define KV_MIX 0
#define O_DEFER 0
#define CH_W2 0
#define HALO_FIRST 1
#define PREV_EARLY 0
#define ACQ 0
#define U_TMA 0
#define U_GATE 0
#define RF_GATE 0
#define WO_TRIG B_WST
#define WL_TRIG B_WOP
#define WO_GATE 1

constexpr uint32_t STAGE_BYTES = 47104, ST_W = 16384, ST_WT = 40960;
constexpr uint32_t O_BYTES = 20480, WO_BYTES = 12800;
constexpr uint32_t OFF_OA = 0;
constexpr uint32_t OFF_QS = 3 * O_BYTES, OFF_QT = OFF_QS + 16384;
constexpr uint32_t OFF_WC = 81920;
constexpr uint32_t OFF_WA = 94720;
constexpr uint32_t OFF_GATE = 145920;
constexpr uint32_t OFF_KVX = 147968;
constexpr uint32_t OFF_D = OFF_GATE + 512;
constexpr uint32_t OFF_CH3 = 163840;
constexpr uint32_t CH_BYTES = 12288, U_BYTES = 4096;
constexpr uint32_t OFF_FT = 225280, OFF_GT = 229376;
constexpr uint32_t OFF_CH0 = 188416;
constexpr uint32_t OFF_KVS = OFF_CH0, KVS_V = 4480, KVS_BYTES = 8576;
constexpr uint32_t OFF_WS = OFF_WA;
__device__ __forceinline__ uint32_t off_us(int s) { return OFF_CH0 + 4096 * ((0x65320 >> (4 * s)) & 7); }
constexpr uint32_t OFF_YT = 163840;
constexpr uint32_t OFF_BAR = 231936;
constexpr uint32_t SMEM_BYTES = OFF_BAR + 512;

enum : uint32_t {
  B_FULL1 = 0, B_EMPTY1 = 4, B_S3 = 7, B_FULL2 = 52, B_EMPTY2 = 13, B_U = 8, B_GATE = 12, B_HA = 19, B_HB = 20,
  B_ATTN = 21, B_C34 = 22, B_CONV = 23, B_YFULL = 24, B_EPOCH = 25, B_PREP = 26, B_P1 = 27, B_LAST = 28,
  B_E3 = 29, B_OSIG = 30, B_WOP = 31, B_USIG = 32, B_WST = 33, B_KV = 34, B_KVD = 39, B_HC = 61, B_QF = 62, B_YST = 40,
  B_US = 45, B_YSIG = 50
};
constexpr uint32_t OFF_EPOCH = OFF_BAR + 8 * 51;
__device__ __forceinline__ uint32_t off_o(int j) { return j < 4 ? OFF_OA + j * O_BYTES : j < 6 ? OFF_CH0 + (j - 4) * O_BYTES : OFF_OA + (j - 6) * O_BYTES; }
__device__ __forceinline__ uint32_t off_w(int j) { return j < 4 ? OFF_WA + j * WO_BYTES : j == 4 ? OFF_KVX : j == 5 ? OFF_WC : OFF_WA + (j - 6) * WO_BYTES; }
__device__ __forceinline__ int step_src(int hg, int j) { return SRC_ROT ? (hg + j) & 7 : j == 0 ? hg : j <= hg ? j - 1 : j; }
__device__ __forceinline__ bool tail_first(int hg) { return TAILF && (hg & 3) == 3; }
__device__ __forceinline__ uint32_t off_ch(int c) { return (c < 3 ? OFF_CH0 : OFF_CH3 - 3 * CH_BYTES) + c * CH_BYTES; }

#define U_PITCH 264
__device__ __align__(1024) uint4 g_U[DIM * U_PITCH];
__device__ uint4 g_O[NCTA * 1280];
#define g_Y g_U
constexpr int Y_PITCH = U_PITCH;
__device__ uint4 g_WO[64 * 800];
__device__ uint4 g_halo[NCTA * 2 * 7 * 32];
__device__ float g_gate[SEQ + PAD_KB * 256];
__device__ unsigned g_cnt[32 * (1 + 2 * 16 + 8 + NCTA)];
constexpr int C_LAUNCH = 0, C_PREP = 32, C_Y = 32 * 17, C_W = 32 * 33, C_O = 32 * 41;

#define TSM(cond, slot) do { } while (0)
#define TSIF(cond, slot) do { if (__LINE__ >= FENCE_LO && __LINE__ < FENCE_HI) sched_fence(); } while (0)
__device__ __forceinline__ void sched_fence() {
  asm volatile("{\n.reg .pred p;\n.reg .u32 c;\nmov.u32 c, %%clock;\nsetp.eq.u32 p, c, 0;\n@p st.shared.u32 [%0], c;\n}"
               ::"r"(1024 + OFF_EPOCH + 4) : "memory");
}
#define TS(slot) TSIF(true, slot)

struct Params {
  const __nv_bfloat16 *q, *k, *v, *shift_k, *ssm_k, *ssm_D, *wqkv, *wo, *gate_w;
  __nv_bfloat16* out;
  uint32_t zero;
};

#define POLL_NS 0
constexpr int SPIN_LIMIT = 1 << 17;

__device__ __forceinline__ void mbar_init(uint32_t bar, uint32_t count) {
  asm volatile("mbarrier.init.shared::cta.b64 [%0], %1;" ::"r"(bar), "r"(count) : "memory");
}
__device__ __forceinline__ void mbar_expect_tx(uint32_t bar, uint32_t bytes) {
  asm volatile("mbarrier.arrive.expect_tx.shared::cta.b64 _, [%0], %1;" ::"r"(bar), "r"(bytes) : "memory");
}
__device__ __forceinline__ void mbar_arrive(uint32_t bar) {
  asm volatile("mbarrier.arrive.shared::cta.b64 _, [%0];" ::"r"(bar) : "memory");
}
__device__ __forceinline__ void mbar_wait(uint32_t bar, uint32_t parity) {
  uint32_t ok;
  int spins = 0;
  do {
    if (WAIT_NS)
      asm volatile("{\n.reg .pred p;\nmbarrier.try_wait.parity.shared::cta.b64 p, [%1], %2, %3;\nselp.b32 %0, 1, 0, p;\n}"
                   : "=r"(ok) : "r"(bar), "r"(parity), "r"(WAIT_NS) : "memory");
    else
      asm volatile("{\n.reg .pred p;\nmbarrier.try_wait.parity.shared::cta.b64 p, [%1], %2;\nselp.b32 %0, 1, 0, p;\n}"
                   : "=r"(ok) : "r"(bar), "r"(parity) : "memory");
    if (++spins > SPIN_LIMIT) break;
  } while (!ok);
}
__device__ __forceinline__ void flag_poll(const unsigned* p, unsigned target) {
  unsigned v;
  int spins = 0;
  do {
    if (POLL_NS && spins) __nanosleep(POLL_NS);
    asm volatile("ld.relaxed.gpu.global.u32 %0, [%1];" : "=r"(v) : "l"(p) : "memory");
    if (++spins > SPIN_LIMIT) break;
  } while ((int)(v - target) < 0);
}
__device__ __forceinline__ void flag_wait(const unsigned* p, unsigned target) {
  flag_poll(p, target);
  if (ACQ) asm volatile("fence.acquire.gpu;\nfence.proxy.async.global;" ::: "memory");
}
__device__ __forceinline__ void flag_signal(unsigned* p, int n, int lane) {
  if (lane == 0) asm volatile("fence.release.gpu;" ::: "memory");
  __syncwarp();
  if (lane < n) asm volatile("red.relaxed.gpu.global.add.u32 [%0], 1;" ::"l"(p + 32 * lane) : "memory");
}
__device__ __forceinline__ void flag_bump(unsigned* p) {
  asm volatile("red.relaxed.gpu.global.add.u32 [%0], 1;" ::"l"(p) : "memory");
}
__device__ __forceinline__ void fence_async_smem() { asm volatile("fence.proxy.async.shared::cta;" ::: "memory"); }
__device__ __forceinline__ void wg_sync(int id) { asm volatile("bar.sync %0, 128;" ::"r"(id) : "memory"); }

__device__ __forceinline__ void tma_2d(uint32_t dst, const CUtensorMap* tm, int c0, int c1, uint32_t bar) {
  asm volatile("cp.async.bulk.tensor.2d.shared::cluster.global.mbarrier::complete_tx::bytes [%0], [%1, {%3, %4}], [%2];"
               ::"r"(dst), "l"(tm), "r"(bar), "r"(c0), "r"(c1) : "memory");
}
__device__ __forceinline__ void tma_3d(uint32_t dst, const CUtensorMap* tm, int c0, int c1, int c2, uint32_t bar) {
  asm volatile("cp.async.bulk.tensor.3d.shared::cluster.global.mbarrier::complete_tx::bytes [%0], [%1, {%3, %4, %5}], [%2];"
               ::"r"(dst), "l"(tm), "r"(bar), "r"(c0), "r"(c1), "r"(c2) : "memory");
}
__device__ __forceinline__ void bulk_load(uint32_t dst, const void* src, uint32_t bytes, uint32_t bar) {
  asm volatile("cp.async.bulk.shared::cluster.global.mbarrier::complete_tx::bytes [%0], [%1], %2, [%3];"
               ::"r"(dst), "l"(src), "r"(bytes), "r"(bar) : "memory");
}
__device__ __forceinline__ void tm_prefetch(const CUtensorMap* tm) {
  asm volatile("prefetch.tensormap [%0];" ::"l"(tm) : "memory");
}

__device__ __forceinline__ void wg_fence() { asm volatile("wgmma.fence.sync.aligned;" ::: "memory"); }
__device__ __forceinline__ void wg_commit() { asm volatile("wgmma.commit_group.sync.aligned;" ::: "memory"); }
template <int N> __device__ __forceinline__ void wg_wait() { asm volatile("wgmma.wait_group.sync.aligned %0;" ::"n"(N) : "memory"); }
__device__ __forceinline__ uint32_t desc_lo(uint32_t addr, uint32_t lbo) { return ((addr & 0x3FFFF) >> 4) | ((lbo >> 4) << 16); }
constexpr uint32_t desc_hi(uint32_t sbo, uint32_t swz) { return (sbo >> 4) | (swz << 30); }
constexpr uint32_t HI_SW128 = desc_hi(1024, 1), HI_SW64 = desc_hi(512, 2), HI_SW32 = desc_hi(256, 3), HI_NONE = desc_hi(128, 0);
template <int N> __device__ __forceinline__ void pin(float* d) {
#pragma unroll
  for (int i = 0; i < N; i++) asm volatile("" : "+f"(d[i])::"memory");
}

__device__ __forceinline__ uint32_t lds32(uint32_t a) {
  uint32_t v;
  asm volatile("ld.volatile.shared.u32 %0, [%1];" : "=r"(v) : "r"(a) : "memory");
  return v;
}
__device__ __forceinline__ uint4 ldg128(const void* a) {
  uint4 v;
  asm volatile("ld.global.nc.v4.u32 {%0, %1, %2, %3}, [%4];" : "=r"(v.x), "=r"(v.y), "=r"(v.z), "=r"(v.w) : "l"(a) : "memory");
  return v;
}
__device__ __forceinline__ uint2 ldg64(const void* a) {
  uint2 v;
  asm volatile("ld.global.nc.v2.u32 {%0, %1}, [%2];" : "=r"(v.x), "=r"(v.y) : "l"(a) : "memory");
  return v;
}
__device__ __forceinline__ void ldsm4(uint32_t* r, uint32_t a) {
  asm volatile("ldmatrix.sync.aligned.m8n8.x4.shared.b16 {%0, %1, %2, %3}, [%4];"
               : "=r"(r[0]), "=r"(r[1]), "=r"(r[2]), "=r"(r[3]) : "r"(a) : "memory");
}
__device__ __forceinline__ void ldsm4t(uint32_t* r, uint32_t a) {
  asm volatile("ldmatrix.sync.aligned.m8n8.x4.trans.shared.b16 {%0, %1, %2, %3}, [%4];"
               : "=r"(r[0]), "=r"(r[1]), "=r"(r[2]), "=r"(r[3]) : "r"(a) : "memory");
}
__device__ __forceinline__ uint4 lds128(uint32_t a) {
  uint4 v;
  asm volatile("ld.shared.v4.u32 {%0, %1, %2, %3}, [%4];" : "=r"(v.x), "=r"(v.y), "=r"(v.z), "=r"(v.w) : "r"(a) : "memory");
  return v;
}
__device__ __forceinline__ void sts128(uint32_t a, uint32_t x, uint32_t y, uint32_t z, uint32_t w) {
  asm volatile("st.shared.v4.u32 [%0], {%1, %2, %3, %4};" ::"r"(a), "r"(x), "r"(y), "r"(z), "r"(w) : "memory");
}
__device__ __forceinline__ void stsm4(uint32_t a, const uint32_t* r) {
  asm volatile("stmatrix.sync.aligned.m8n8.x4.shared.b16 [%0], {%1, %2, %3, %4};" ::"r"(a), "r"(r[0]), "r"(r[1]), "r"(r[2]), "r"(r[3]) : "memory");
}
__device__ __forceinline__ void stsm4t(uint32_t a, const uint32_t* r) {
  asm volatile("stmatrix.sync.aligned.m8n8.x4.trans.shared.b16 [%0], {%1, %2, %3, %4};" ::"r"(a), "r"(r[0]), "r"(r[1]), "r"(r[2]), "r"(r[3]) : "memory");
}
__device__ __forceinline__ uint32_t pack2(float lo, float hi) {
  uint32_t r;
  asm("cvt.rn.bf16x2.f32 %0, %1, %2;" : "=r"(r) : "f"(hi), "f"(lo));
  return r;
}
__device__ __forceinline__ uint32_t movm(uint32_t a) {
  uint32_t d;
  asm volatile("movmatrix.sync.aligned.m8n8.trans.b16 %0, %1;" : "=r"(d) : "r"(a));
  return d;
}
__device__ __forceinline__ uint32_t bmul(uint32_t a, uint32_t b) {
  uint32_t d;
  asm("mul.rn.bf16x2 %0, %1, %2;" : "=r"(d) : "r"(a), "r"(b));
  return d;
}
__device__ __forceinline__ uint32_t badd(uint32_t a, uint32_t b) {
  uint32_t d;
  asm("add.rn.bf16x2 %0, %1, %2;" : "=r"(d) : "r"(a), "r"(b));
  return d;
}
__device__ __forceinline__ float bf_lo(uint32_t x) { return __uint_as_float(x << 16); }
__device__ __forceinline__ float bf_hi(uint32_t x) { return __uint_as_float(x & 0xFFFF0000u); }
__device__ __forceinline__ float ex2(float x) {
  float y;
  asm("ex2.approx.ftz.f32 %0, %1;" : "=f"(y) : "f"(x));
  return y;
}
__device__ __forceinline__ float rcp(float x) {
  float y;
  asm("rcp.approx.ftz.f32 %0, %1;" : "=f"(y) : "f"(x));
  return y;
}
__device__ __forceinline__ void mma16816(float* d, uint32_t a0, uint32_t a1, uint32_t a2, uint32_t a3, uint32_t b0, uint32_t b1) {
  asm volatile("mma.sync.aligned.m16n8k16.row.col.f32.bf16.bf16.f32 {%0, %1, %2, %3}, {%4, %5, %6, %7}, {%8, %9}, {%0, %1, %2, %3};"
               : "+f"(d[0]), "+f"(d[1]), "+f"(d[2]), "+f"(d[3])
               : "r"(a0), "r"(a1), "r"(a2), "r"(a3), "r"(b0), "r"(b1));
}
__device__ __forceinline__ void mma1688(float* d, uint32_t a0, uint32_t a1, uint32_t b0) {
  asm volatile("mma.sync.aligned.m16n8k8.row.col.f32.bf16.bf16.f32 {%0, %1, %2, %3}, {%4, %5}, {%6}, {%0, %1, %2, %3};"
               : "+f"(d[0]), "+f"(d[1]), "+f"(d[2]), "+f"(d[3])
               : "r"(a0), "r"(a1), "r"(b0));
}

template <int N> struct WgRS;
template <int N> struct WgSST;
template <> struct WgRS<32> {
  template <uint32_t HB>
  static __device__ __forceinline__ void mma(float* d, const uint32_t* a, uint32_t db) {
    asm volatile("{\n.reg .pred p;\n.reg .b64 db;\nsetp.ne.b32 p, %22, 0;\n"
      "mov.b64 db, {%20, %21};\n"
      "wgmma.mma_async.sync.aligned.m64n32k16.f32.bf16.bf16 {"
      "%0, %1, %2, %3, %4, %5, %6, %7, %8, %9, %10, %11, %12, %13, %14, %15"
      "}, {%16, %17, %18, %19}, db, p, 1, 1, 1;\n}\n"
      : "+f"(d[0]), "+f"(d[1]), "+f"(d[2]), "+f"(d[3]), "+f"(d[4]), "+f"(d[5]), "+f"(d[6]), "+f"(d[7]),
        "+f"(d[8]), "+f"(d[9]), "+f"(d[10]), "+f"(d[11]), "+f"(d[12]), "+f"(d[13]), "+f"(d[14]), "+f"(d[15])
      : "r"(a[0]), "r"(a[1]), "r"(a[2]), "r"(a[3]), "r"(db), "n"(HB), "n"(1));
  }
  template <uint32_t HB>
  static __device__ __forceinline__ void set(float* d, const uint32_t* a, uint32_t db) {
    asm volatile("{\n.reg .pred p;\n.reg .b64 db;\nsetp.ne.b32 p, %22, 0;\n"
      "mov.b64 db, {%20, %21};\n"
      "wgmma.mma_async.sync.aligned.m64n32k16.f32.bf16.bf16 {"
      "%0, %1, %2, %3, %4, %5, %6, %7, %8, %9, %10, %11, %12, %13, %14, %15"
      "}, {%16, %17, %18, %19}, db, p, 1, 1, 1;\n}\n"
      : "=f"(d[0]), "=f"(d[1]), "=f"(d[2]), "=f"(d[3]), "=f"(d[4]), "=f"(d[5]), "=f"(d[6]), "=f"(d[7]),
        "=f"(d[8]), "=f"(d[9]), "=f"(d[10]), "=f"(d[11]), "=f"(d[12]), "=f"(d[13]), "=f"(d[14]), "=f"(d[15])
      : "r"(a[0]), "r"(a[1]), "r"(a[2]), "r"(a[3]), "r"(db), "n"(HB), "n"(0));
  }
};
template <> struct WgRS<64> {
  template <uint32_t HB>
  static __device__ __forceinline__ void mma(float* d, const uint32_t* a, uint32_t db) {
    asm volatile("{\n.reg .pred p;\n.reg .b64 db;\nsetp.ne.b32 p, %38, 0;\n"
      "mov.b64 db, {%36, %37};\n"
      "wgmma.mma_async.sync.aligned.m64n64k16.f32.bf16.bf16 {"
      "%0, %1, %2, %3, %4, %5, %6, %7, %8, %9, %10, %11, %12, %13, %14, %15, "
      "%16, %17, %18, %19, %20, %21, %22, %23, %24, %25, %26, %27, %28, %29, %30, %31"
      "}, {%32, %33, %34, %35}, db, p, 1, 1, 1;\n}\n"
      : "+f"(d[0]), "+f"(d[1]), "+f"(d[2]), "+f"(d[3]), "+f"(d[4]), "+f"(d[5]), "+f"(d[6]), "+f"(d[7]),
        "+f"(d[8]), "+f"(d[9]), "+f"(d[10]), "+f"(d[11]), "+f"(d[12]), "+f"(d[13]), "+f"(d[14]), "+f"(d[15]),
        "+f"(d[16]), "+f"(d[17]), "+f"(d[18]), "+f"(d[19]), "+f"(d[20]), "+f"(d[21]), "+f"(d[22]), "+f"(d[23]),
        "+f"(d[24]), "+f"(d[25]), "+f"(d[26]), "+f"(d[27]), "+f"(d[28]), "+f"(d[29]), "+f"(d[30]), "+f"(d[31])
      : "r"(a[0]), "r"(a[1]), "r"(a[2]), "r"(a[3]), "r"(db), "n"(HB), "n"(1));
  }
  template <uint32_t HB>
  static __device__ __forceinline__ void set(float* d, const uint32_t* a, uint32_t db) {
    asm volatile("{\n.reg .pred p;\n.reg .b64 db;\nsetp.ne.b32 p, %38, 0;\n"
      "mov.b64 db, {%36, %37};\n"
      "wgmma.mma_async.sync.aligned.m64n64k16.f32.bf16.bf16 {"
      "%0, %1, %2, %3, %4, %5, %6, %7, %8, %9, %10, %11, %12, %13, %14, %15, "
      "%16, %17, %18, %19, %20, %21, %22, %23, %24, %25, %26, %27, %28, %29, %30, %31"
      "}, {%32, %33, %34, %35}, db, p, 1, 1, 1;\n}\n"
      : "=f"(d[0]), "=f"(d[1]), "=f"(d[2]), "=f"(d[3]), "=f"(d[4]), "=f"(d[5]), "=f"(d[6]), "=f"(d[7]),
        "=f"(d[8]), "=f"(d[9]), "=f"(d[10]), "=f"(d[11]), "=f"(d[12]), "=f"(d[13]), "=f"(d[14]), "=f"(d[15]),
        "=f"(d[16]), "=f"(d[17]), "=f"(d[18]), "=f"(d[19]), "=f"(d[20]), "=f"(d[21]), "=f"(d[22]), "=f"(d[23]),
        "=f"(d[24]), "=f"(d[25]), "=f"(d[26]), "=f"(d[27]), "=f"(d[28]), "=f"(d[29]), "=f"(d[30]), "=f"(d[31])
      : "r"(a[0]), "r"(a[1]), "r"(a[2]), "r"(a[3]), "r"(db), "n"(HB), "n"(0));
  }
};
template <> struct WgSST<48> {
  template <uint32_t HA, uint32_t HB>
  static __device__ __forceinline__ void mma(float* d, uint32_t da, uint32_t db, int sc) {
    asm volatile("{\n.reg .pred p;\n.reg .b64 da, db;\nsetp.ne.b32 p, %28, 0;\n"
      "mov.b64 da, {%24, %25};\nmov.b64 db, {%26, %27};\n"
      "wgmma.mma_async.sync.aligned.m64n48k16.f32.bf16.bf16 {"
      "%0, %1, %2, %3, %4, %5, %6, %7, %8, %9, %10, %11, %12, %13, %14, %15, "
      "%16, %17, %18, %19, %20, %21, %22, %23"
      "}, da, db, p, 1, 1, 0, 1;\n}\n"
      : "+f"(d[0]), "+f"(d[1]), "+f"(d[2]), "+f"(d[3]), "+f"(d[4]), "+f"(d[5]), "+f"(d[6]), "+f"(d[7]),
        "+f"(d[8]), "+f"(d[9]), "+f"(d[10]), "+f"(d[11]), "+f"(d[12]), "+f"(d[13]), "+f"(d[14]), "+f"(d[15]),
        "+f"(d[16]), "+f"(d[17]), "+f"(d[18]), "+f"(d[19]), "+f"(d[20]), "+f"(d[21]), "+f"(d[22]), "+f"(d[23])
      : "r"(da), "n"(HA), "r"(db), "n"(HB), "r"(sc));
  }
};
template <> struct WgSST<80> {
  template <uint32_t HA, uint32_t HB>
  static __device__ __forceinline__ void mma(float* d, uint32_t da, uint32_t db, int sc) {
    asm volatile("{\n.reg .pred p;\n.reg .b64 da, db;\nsetp.ne.b32 p, %44, 0;\n"
      "mov.b64 da, {%40, %41};\nmov.b64 db, {%42, %43};\n"
      "wgmma.mma_async.sync.aligned.m64n80k16.f32.bf16.bf16 {"
      "%0, %1, %2, %3, %4, %5, %6, %7, %8, %9, %10, %11, %12, %13, %14, %15, "
      "%16, %17, %18, %19, %20, %21, %22, %23, %24, %25, %26, %27, %28, %29, %30, %31, "
      "%32, %33, %34, %35, %36, %37, %38, %39"
      "}, da, db, p, 1, 1, 0, 1;\n}\n"
      : "+f"(d[0]), "+f"(d[1]), "+f"(d[2]), "+f"(d[3]), "+f"(d[4]), "+f"(d[5]), "+f"(d[6]), "+f"(d[7]),
        "+f"(d[8]), "+f"(d[9]), "+f"(d[10]), "+f"(d[11]), "+f"(d[12]), "+f"(d[13]), "+f"(d[14]), "+f"(d[15]),
        "+f"(d[16]), "+f"(d[17]), "+f"(d[18]), "+f"(d[19]), "+f"(d[20]), "+f"(d[21]), "+f"(d[22]), "+f"(d[23]),
        "+f"(d[24]), "+f"(d[25]), "+f"(d[26]), "+f"(d[27]), "+f"(d[28]), "+f"(d[29]), "+f"(d[30]), "+f"(d[31]),
        "+f"(d[32]), "+f"(d[33]), "+f"(d[34]), "+f"(d[35]), "+f"(d[36]), "+f"(d[37]), "+f"(d[38]), "+f"(d[39])
      : "r"(da), "n"(HA), "r"(db), "n"(HB), "r"(sc));
  }
};
template <> struct WgSST<192> {
  template <uint32_t HA, uint32_t HB>
  static __device__ __forceinline__ void mma(float* d, uint32_t da, uint32_t db, int sc) {
    asm volatile("{\n.reg .pred p;\n.reg .b64 da, db;\nsetp.ne.b32 p, %100, 0;\n"
      "mov.b64 da, {%96, %97};\nmov.b64 db, {%98, %99};\n"
      "wgmma.mma_async.sync.aligned.m64n192k16.f32.bf16.bf16 {"
      "%0, %1, %2, %3, %4, %5, %6, %7, %8, %9, %10, %11, %12, %13, %14, %15, "
      "%16, %17, %18, %19, %20, %21, %22, %23, %24, %25, %26, %27, %28, %29, %30, %31, "
      "%32, %33, %34, %35, %36, %37, %38, %39, %40, %41, %42, %43, %44, %45, %46, %47, "
      "%48, %49, %50, %51, %52, %53, %54, %55, %56, %57, %58, %59, %60, %61, %62, %63, "
      "%64, %65, %66, %67, %68, %69, %70, %71, %72, %73, %74, %75, %76, %77, %78, %79, "
      "%80, %81, %82, %83, %84, %85, %86, %87, %88, %89, %90, %91, %92, %93, %94, %95"
      "}, da, db, p, 1, 1, 0, 1;\n}\n"
      : "+f"(d[0]), "+f"(d[1]), "+f"(d[2]), "+f"(d[3]), "+f"(d[4]), "+f"(d[5]), "+f"(d[6]), "+f"(d[7]),
        "+f"(d[8]), "+f"(d[9]), "+f"(d[10]), "+f"(d[11]), "+f"(d[12]), "+f"(d[13]), "+f"(d[14]), "+f"(d[15]),
        "+f"(d[16]), "+f"(d[17]), "+f"(d[18]), "+f"(d[19]), "+f"(d[20]), "+f"(d[21]), "+f"(d[22]), "+f"(d[23]),
        "+f"(d[24]), "+f"(d[25]), "+f"(d[26]), "+f"(d[27]), "+f"(d[28]), "+f"(d[29]), "+f"(d[30]), "+f"(d[31]),
        "+f"(d[32]), "+f"(d[33]), "+f"(d[34]), "+f"(d[35]), "+f"(d[36]), "+f"(d[37]), "+f"(d[38]), "+f"(d[39]),
        "+f"(d[40]), "+f"(d[41]), "+f"(d[42]), "+f"(d[43]), "+f"(d[44]), "+f"(d[45]), "+f"(d[46]), "+f"(d[47]),
        "+f"(d[48]), "+f"(d[49]), "+f"(d[50]), "+f"(d[51]), "+f"(d[52]), "+f"(d[53]), "+f"(d[54]), "+f"(d[55]),
        "+f"(d[56]), "+f"(d[57]), "+f"(d[58]), "+f"(d[59]), "+f"(d[60]), "+f"(d[61]), "+f"(d[62]), "+f"(d[63]),
        "+f"(d[64]), "+f"(d[65]), "+f"(d[66]), "+f"(d[67]), "+f"(d[68]), "+f"(d[69]), "+f"(d[70]), "+f"(d[71]),
        "+f"(d[72]), "+f"(d[73]), "+f"(d[74]), "+f"(d[75]), "+f"(d[76]), "+f"(d[77]), "+f"(d[78]), "+f"(d[79]),
        "+f"(d[80]), "+f"(d[81]), "+f"(d[82]), "+f"(d[83]), "+f"(d[84]), "+f"(d[85]), "+f"(d[86]), "+f"(d[87]),
        "+f"(d[88]), "+f"(d[89]), "+f"(d[90]), "+f"(d[91]), "+f"(d[92]), "+f"(d[93]), "+f"(d[94]), "+f"(d[95])
      : "r"(da), "n"(HA), "r"(db), "n"(HB), "r"(sc));
  }
};

struct FftConst {
  uint32_t f[2][4], fi[4][4];
  float ta[4], tb[4];
};
__device__ __forceinline__ void cis(int m, float scale, float& c, float& s) {
  const float a = (float)m * (-6.283185307179586f * scale);
  c = __cosf(a);
  s = __sinf(a);
}
__device__ __forceinline__ void fft_tables(uint32_t (&v)[12], int tw) {
  const int row = tw >> 2, ch = tw & 3;
#pragma unroll
  for (int i = 0; i < 4; i++) {
    float c[2], s[2], x[2];
#pragma unroll
    for (int e = 0; e < 2; e++) {
      cis((((32 * (8 * ch + 2 * i + e) + 15) * (4 * row - 63) + 2048) & 4095) - 2048, 1.f / 4096, c[e], s[e]);
      float gc, gs;
      cis((((row & 15) * (8 * (ch & 1) + 2 * i + e) + 8) & 15) - 8, 1.f / 16, gc, gs);
      x[e] = (row >> 4) == (ch >> 1) ? gc : (ch >> 1) ? gs : -gs;
    }
    v[i] = pack2(c[0] * 0.125f, c[1] * 0.125f);
    v[4 + i] = pack2(s[0] * 0.125f, s[1] * 0.125f);
    v[8 + i] = pack2(x[0], x[1]);
  }
#pragma unroll
  for (int i = 0; i < 12; i++) asm volatile("" : "+r"(v[i]));
}
__device__ __forceinline__ void fft_tables_store(const uint32_t (&v)[12], uint32_t sb, int tw) {
  const int row = tw >> 2;
  const uint32_t x = ((tw ^ (row >> 1)) & 3) << 4, a = sb + OFF_FT + (16 * (row >> 3) + (row & 7)) * 64 + x;
  sts128(a, v[0], v[1], v[2], v[3]);
  sts128(a + 512, v[4], v[5], v[6], v[7]);
  sts128(sb + OFF_GT + row * 64 + x, v[8], v[9], v[10], v[11]);
}
__device__ __forceinline__ void fft_twiddles(FftConst& k, int w, int lane) {
#pragma unroll
  for (int i = 0; i < 4; i++) {
    float c, s;
    cis((2 * (8 * (i >> 1) + 2 * (lane & 3) + (i & 1)) - 15) * (4 * (8 * w + (lane >> 2)) - 63), 1.f / 4096, c, s);
    k.ta[i] = __fdividef(-s, 1.f + c);
    k.tb[i] = s;
  }
  pin<4>(k.ta);
  pin<4>(k.tb);
}
__device__ __forceinline__ void fft_matrices(FftConst& k, uint32_t sb, int w, int lane) {
  const uint32_t x = (lane >> 1) & 3;
#pragma unroll
  for (int i = 0; i < 2; i++) {
    ldsm4(k.f[i], sb + OFF_FT + (16 * w + (lane & 15)) * 64 + (((2 * i + (lane >> 4)) ^ x) << 4));
    ldsm4t(k.fi[i], sb + OFF_FT + (32 * i + lane) * 64 + ((w ^ x) << 4));
#pragma unroll
    for (int j = 0; j < 4; j++) {
      k.fi[2 + i][j] = (j & 1) ? k.fi[i][j - 1] ^ 0x80008000u : k.fi[i][j + 1];
      asm volatile("" : "+r"(k.fi[2 + i][j]));
    }
  }
}
template <bool INV> __device__ __forceinline__ void rot(float& x, float& y, float a, float b) {
  x = fmaf(INV ? -a : a, y, x);
  y = fmaf(INV ? -b : b, x, y);
  x = fmaf(INV ? -a : a, y, x);
}
__device__ __forceinline__ void twiddle_fwd(uint32_t (&a)[4][4], float* d, const FftConst& k) {
#pragma unroll
  for (int q = 0; q < 4; q++)
#pragma unroll
    for (int j = 0; j < 2; j++) {
      float* x = d + 8 * q + 4 * j;
      rot<false>(x[0], x[2], k.ta[2 * j], k.tb[2 * j]);
      rot<false>(x[1], x[3], k.ta[2 * j + 1], k.tb[2 * j + 1]);
      a[q & 2][2 * j + (q & 1)] = pack2(x[0], x[1]);
      a[(q & 2) + 1][2 * j + (q & 1)] = pack2(x[2], x[3]);
    }
}
__device__ __forceinline__ void g_step(float* d, const uint32_t (&a)[4][4], uint32_t dre, uint32_t dim) {
  WgRS<32>::set<HI_SW64>(d, a[0], dre);
  WgRS<32>::set<HI_SW64>(d + 16, a[2], dre);
  WgRS<32>::mma<HI_SW64>(d, a[1], dim);
  WgRS<32>::mma<HI_SW64>(d + 16, a[3], dim);
  wg_commit();
}

__device__ __forceinline__ void conv_channel(const FftConst& k, uint32_t sb, int c, int wg, int w, int lane) {
  const uint32_t cb = sb + off_ch(c), bars = sb + OFF_BAR;
  const uint32_t du = desc_lo(cb, 1024), dg = desc_lo(sb + OFF_GT, 16), dz = desc_lo(cb + U_BYTES, 16);
  float U[32], H[32];
  uint32_t a[4][4], e[4][4];
  const float dv = __uint_as_float(lds32(sb + OFF_D + 4 * c));
  wg_fence();
  WgRS<64>::set<HI_SW32>(H, k.f[0], du + 256);
  WgRS<64>::mma<HI_SW32>(H, k.f[1], du + 256 + 32);
  wg_commit();
  wg_wait<0>();
  pin<32>(H);
  twiddle_fwd(a, H, k);
  if (ATT_GATE && H_EARLY) mbar_wait(bars + 8 * B_ATTN, 0);
  mbar_wait(bars + 8 * (B_U + (c < 3 ? c : 3)), 0);
  TSM(w == 0 && c < 3, 7 + wg);
  wg_fence();
  WgRS<64>::set<HI_SW32>(U, k.f[0], du);
  WgRS<64>::mma<HI_SW32>(U, k.f[1], du + 32);
  wg_commit();
  g_step(H, a, dg, dg + 64);
  wg_wait<1>();
  pin<32>(U);
  twiddle_fwd(e, U, k);
  wg_fence();
  g_step(U, e, dg, dg + 64);
  wg_wait<0>();
  pin<32>(U);
  pin<32>(H);
#pragma unroll
  for (int j = 0; j < 2; j++) {
    float pr[4][2], pi[4][2];
#pragma unroll
    for (int x = 0; x < 2; x++) {
      H[4 * j + x] += dv;
#pragma unroll
      for (int m = 0; m < 4; m++) {
#pragma unroll
        for (int q = 0; q <= m; q++) {
          const int ih = 16 * (q >> 1) + 2 * (q & 1) + 4 * j + x, iu = 16 * ((m - q) >> 1) + 2 * ((m - q) & 1) + 4 * j + x;
          pr[m][x] = q ? fmaf(H[ih], U[iu], pr[m][x]) : H[ih] * U[iu];
          pi[m][x] = q ? fmaf(H[ih], U[iu + 8], pi[m][x]) : H[ih] * U[iu + 8];
          pr[m][x] = fmaf(-H[ih + 8], U[iu + 8], pr[m][x]);
          pi[m][x] = fmaf(H[ih + 8], U[iu], pi[m][x]);
        }
      }
    }
#pragma unroll
    for (int m = 0; m < 4; m++) {
      a[m & 2][2 * j + (m & 1)] = pack2(pr[m][0], pr[m][1]);
      a[(m & 2) + 1][2 * j + (m & 1)] = pack2(pi[m][0], pi[m][1]);
    }
  }
  wg_fence();
  g_step(U, a, dg + 64, dg);
  const uint32_t za = cb + U_BYTES + (8 * w + (lane & 7)) * 128 + (((lane >> 3) ^ (lane & 7)) << 4);
  const uint32_t ya = cb + (lane >> 4) * 1024 + (8 * w + (lane & 7)) * 32 + ((((lane >> 3) ^ (lane >> 2)) & 1) << 4);
  wg_sync(1 + wg);
  wg_wait<0>();
  pin<32>(U);
  TSIF(w == 0, 80 + c);
#pragma unroll
  for (int p = 0; p < 2; p++) {
#pragma unroll
    for (int i = 0; i < 4; i++) {
      const int j = i & 1;
      float* x = U + 16 * p + 4 * j + (i & 2);
      rot<true>(x[8], x[0], k.ta[2 * j], k.tb[2 * j]);
      rot<true>(x[9], x[1], k.ta[2 * j + 1], k.tb[2 * j + 1]);
      e[p][i] = pack2(x[8], x[9]);
      e[2 + p][i] = pack2(x[0], x[1]);
    }
    stsm4(za ^ (64 * p), e[p]);
    stsm4((za ^ (64 * p)) + 4096, e[2 + p]);
  }
  fence_async_smem();
  wg_sync(1 + wg);
  wg_fence();
  WgRS<64>::set<HI_SW128>(H, k.fi[0], dz);
#pragma unroll
  for (int ks = 1; ks < 4; ks++) WgRS<64>::mma<HI_SW128>(H, k.fi[ks], dz + 128 * ks);
  wg_commit();
  wg_wait<0>();
  pin<32>(H);
  TSIF(w == 0, 88 + c);
#pragma unroll
  for (int j = 0; j < 8; j++)
    a[j >> 2][j & 3] = j < 2 ? pack2(H[4 * j], H[4 * j + 1]) : pack2(H[4 * j] + H[4 * j - 6], H[4 * j + 1] + H[4 * j - 5]);
  stsm4(ya, a[0]);
  stsm4(ya + 2048, a[1]);
  fence_async_smem();
  __syncwarp();
}

__device__ __forceinline__ void prep_slab(uint4* res, const uint2* sw, uint32_t sb, int slab, int w, int lane) {
  const int t = lane & 3, tp = (lane & 7) >> 1, pos = 8 * tp + 2 * (((lane >> 3) + tp) & 3) + (lane & 1);
  const uint32_t base = sb + OFF_KVS + slab * KVS_BYTES + pos * 128;
  uint32_t kk[2][4][4], vv[2][4];
  mbar_wait(sb + OFF_BAR + 8 * (B_KV + slab), 0);
#pragma unroll
  for (int h = 0; h < 2; h++) {
#pragma unroll
    for (int j = 0; j < 4; j++) {
      const uint32_t a = base + 128 * j;
      ldsm4t(kk[h][j], a + (((w + 4 * h) ^ ((a >> 7) & 7)) << 4));
    }
    const uint32_t a = base + KVS_V;
    ldsm4t(vv[h], a + (((w + 4 * h) ^ ((a >> 7) & 7)) << 4));
  }
#pragma unroll
  for (int h = 0; h < 2; h++) {
    uint32_t (&k)[4][4] = kk[h];
    uint32_t (&v)[4] = vv[h];
    const uint32_t w0 = __byte_perm(sw[h].x, 0, 0x1010), w1 = __byte_perm(sw[h].x, 0, 0x3232);
    const uint32_t w2 = __byte_perm(sw[h].y, 0, 0x1010), w3 = __byte_perm(sw[h].y, 0, 0x3232);
#pragma unroll
    for (int m = 0; m < 4; m++)
      v[m] = bmul(badd(badd(badd(bmul(k[0][m], w3), bmul(k[1][m], w2)), bmul(k[2][m], w1)), bmul(k[3][m], w0)), v[m]);
    uint32_t a[4];
#pragma unroll
    for (int m = 0; m < 4; m++) a[m] = (t & 1) ? v[(m + 3) & 3] : v[m];
    res[h] = (t & 2) ? make_uint4(a[2], a[3], a[0], a[1]) : make_uint4(a[0], a[1], a[2], a[3]);
  }
}

__device__ __forceinline__ void prep_gate(const Params& p, int b, int w, int lane) {
  uint2 gw[5], x[4][5];
#pragma unroll
  for (int j = 0; j < 5; j++) gw[j] = ldg64(reinterpret_cast<const uint2*>(p.gate_w) + lane + 32 * j);
#pragma unroll
  for (int i = 0; i < 4; i++)
#pragma unroll
    for (int j = 0; j < 5; j++)
      x[i][j] = ldg64(reinterpret_cast<const uint2*>(p.q) + (16 * b + 4 * w + i) * (DIM / 4) + lane + 32 * j);
  float s[4];
#pragma unroll
  for (int i = 0; i < 4; i++) {
    s[i] = 0.f;
#pragma unroll
    for (int j = 0; j < 5; j++) {
      const uint32_t m0 = bmul(x[i][j].x, gw[j].x), m1 = bmul(x[i][j].y, gw[j].y);
      s[i] += (bf_lo(m0) + bf_hi(m0)) + (bf_lo(m1) + bf_hi(m1));
    }
  }
  const bool h = lane & 16, q = lane & 8;
  const float a = (h ? s[2] : s[0]) + __shfl_xor_sync(0xffffffffu, h ? s[0] : s[2], 16);
  const float c = (h ? s[3] : s[1]) + __shfl_xor_sync(0xffffffffu, h ? s[1] : s[3], 16);
  float z = (q ? c : a) + __shfl_xor_sync(0xffffffffu, q ? a : c, 8);
#pragma unroll
  for (int o = 4; o > 0; o >>= 1) z += __shfl_xor_sync(0xffffffffu, z, o);
  z = bf_lo(pack2(z, 0.f));
  if ((lane & 7) == 0) g_gate[16 * b + 4 * w + (lane >> 3)] = bf_lo(pack2(__fdividef(1.f, 1.f + __expf(-z)), 0.f));
}

__device__ __forceinline__ uint32_t bmax(uint32_t a, uint32_t b) {
  uint32_t d;
  asm("max.bf16x2 %0, %1, %2;" : "=r"(d) : "r"(a), "r"(b));
  return d;
}
__device__ __forceinline__ void softmax_two(const float (&l)[2][2], uint32_t& p0, uint32_t& p1) {
  constexpr float kScale = 0.22360679774997896f, kLog2e = 1.4426950408889634f;
  const uint32_t r0 = pack2(l[0][0], l[1][0]), r1 = pack2(l[0][1], l[1][1]);
  const uint32_t x0 = pack2(bf_lo(r0) * kScale, bf_hi(r0) * kScale), x1 = pack2(bf_lo(r1) * kScale, bf_hi(r1) * kScale);
  uint32_t m = bmax(x0, x1);
  m = bmax(m, __shfl_xor_sync(0xffffffffu, m, 1));
  m = bmax(m, __shfl_xor_sync(0xffffffffu, m, 2));
  const float m0 = bf_lo(m) * kLog2e, m1 = bf_hi(m) * kLog2e;
  p0 = pack2(ex2(bf_lo(x0) * kLog2e - m0), ex2(bf_lo(x1) * kLog2e - m0));
  p1 = pack2(ex2(bf_hi(x0) * kLog2e - m1), ex2(bf_hi(x1) * kLog2e - m1));
}

__device__ __forceinline__ void halo_read(uint32_t (&kpv)[10], uint32_t (&vpv)[10], uint32_t (&tg)[7], const uint4* hp) {
#pragma unroll
  for (int j = 0; j < 7; j++) {
    uint32_t x0, x1, x2;
    asm volatile("ld.relaxed.gpu.global.v4.u32 {%0, %1, %2, %3}, [%4];"
                 : "=r"(x0), "=r"(x1), "=r"(x2), "=r"(tg[j]) : "l"(hp + 32 * j) : "memory");
    if (j < 4) kpv[3 * j] = x0; else vpv[3 * j - 10] = x0;
    if (j < 3) kpv[3 * j + 1] = x1; else vpv[3 * j - 9] = x1;
    if (j < 3) kpv[3 * j + 2] = x2; else if (j < 6) vpv[3 * j - 8] = x2;
  }
}

template <int ROT>
__device__ __forceinline__ void pack_qkv(const float* acc, uint32_t (&qlo)[10], uint32_t (&qhi)[10], uint32_t (&klo)[10],
                                         uint32_t (&khi)[10], uint32_t (&vlo)[10], uint32_t (&vhi)[10]) {
#pragma unroll
  for (int j = 0; j < 10; j++) {
    const int x = (j + ROT) % 10, tq = x < 8 ? x : 16 + x, tk = x < 8 ? 8 + x : 18 + x, tv = x < 8 ? 16 + x : 20 + x;
    khi[j] = pack2(acc[4 * tk + 2], acc[4 * tk + 3]);
    vhi[j] = movm(pack2(acc[4 * tv + 2], acc[4 * tv + 3]));
    qlo[j] = pack2(acc[4 * tq], acc[4 * tq + 1]);
    qhi[j] = pack2(acc[4 * tq + 2], acc[4 * tq + 3]);
    klo[j] = pack2(acc[4 * tk], acc[4 * tk + 1]);
    vlo[j] = pack2(acc[4 * tv], acc[4 * tv + 1]);
    asm volatile("" : "+r"(khi[j]), "+r"(qlo[j]), "+r"(qhi[j]), "+r"(klo[j]), "+r"(vlo[j]));
  }
}

template <int ROT> __device__ __forceinline__ void halo_send(const float* acc, uint4* ho, uint32_t tag) {
#pragma unroll
  for (int j = 0; j < 7; j++) {
    uint32_t x[3];
#pragma unroll
    for (int e = 0; e < 3; e++) {
      const int i = 3 * j + e, y = (i % 10 + ROT) % 10, tk = y < 8 ? 8 + y : 18 + y, tv = y < 8 ? 16 + y : 20 + y;
      x[e] = i < 10 ? pack2(acc[4 * tk + 2], acc[4 * tk + 3]) : i < 20 ? movm(pack2(acc[4 * tv + 2], acc[4 * tv + 3])) : 0u;
    }
    asm volatile("st.relaxed.gpu.global.v4.u32 [%0], {%1, %2, %3, %4};" ::"l"(ho + 32 * j), "r"(x[0]), "r"(x[1]), "r"(x[2]), "r"(tag) : "memory");
  }
}

__device__ __forceinline__ void attention(float* acc, uint32_t sb, int b, int par, int w, int lane, uint32_t tag) {
  const int g = lane >> 2, t = lane & 3;
  uint32_t klo[10], khi[10], vlo[10], vhi[10], qlo[10], qhi[10], kpv[10], vpv[10];
  if (HALO_FIRST && w == 3 && b < NCTA - 8) {
    uint4* ho = g_halo + (b * 2 + par) * 224 + lane;
    if (tail_first(b & 7)) halo_send<8>(acc, ho, tag);
    else halo_send<0>(acc, ho, tag);
    TSIF(par == 0, 76);
    pin<120>(acc);
  }
  if (tail_first(b & 7)) pack_qkv<8>(acc, qlo, qhi, klo, khi, vlo, vhi);
  else pack_qkv<0>(acc, qlo, qhi, klo, khi, vlo, vhi);
  const uint32_t xa = sb + OFF_KVX + (par * 3) * 2560 + lane * 16;
  if (w < 3) {
    sts128(xa + w * 2560, khi[0], khi[1], khi[2], khi[3]);
    sts128(xa + w * 2560 + 512, khi[4], khi[5], khi[6], khi[7]);
    sts128(xa + w * 2560 + 1024, khi[8], khi[9], vhi[0], vhi[1]);
    sts128(xa + w * 2560 + 1536, vhi[2], vhi[3], vhi[4], vhi[5]);
    sts128(xa + w * 2560 + 2048, vhi[6], vhi[7], vhi[8], vhi[9]);
  } else if (!HALO_FIRST && b < NCTA - 8) {
    uint4* ho = g_halo + (b * 2 + par) * 224 + lane;
#pragma unroll
    for (int j = 0; j < 7; j++) {
      const uint32_t x0 = j < 4 ? khi[3 * j] : vhi[3 * j - 10], x1 = j < 3 ? khi[3 * j + 1] : vhi[3 * j - 9];
      const uint32_t x2 = j < 3 ? khi[3 * j + 2] : j < 6 ? vhi[3 * j - 8] : 0u;
      asm volatile("st.relaxed.gpu.global.v4.u32 [%0], {%1, %2, %3, %4};" ::"l"(ho + 32 * j), "r"(x0), "r"(x1), "r"(x2), "r"(tag) : "memory");
    }
  }
  TSIF(par == 0 && w == 1, 64);
  TSIF(par == 0 && w == 3 && !HALO_FIRST, 76);
#pragma unroll
  for (int j = 0; j < 10; j++) vlo[j] = movm(vlo[j]);
  const bool far0 = 2 * t > g, far1 = 2 * t + 1 > g;
  const uint32_t mfar = (far0 ? 0x0000FFFFu : 0u) | (far1 ? 0xFFFF0000u : 0u);
  float slo[4][2], shi[4][2], lg[2][2];
  uint32_t phi[4], plo[4], qml[4], qmh[4];
#pragma unroll
  for (int h = 0; h < 4; h++) {
    const int f = h == 0 ? 0 : h == 1 ? 3 : h == 2 ? 5 : 8, hf = h < 2 ? 2 : 7;
    const bool mine = (h & 1) ? t >= 2 : t < 2;
    qml[h] = mine ? qlo[hf] : 0u;
    qmh[h] = mine ? qhi[hf] : 0u;
    float a[4] = {0.f, 0.f, 0.f, 0.f}, c[4] = {0.f, 0.f, 0.f, 0.f};
    mma16816(a, qlo[f], qhi[f], qlo[f + 1], qhi[f + 1], klo[f], klo[f + 1]);
    mma16816(c, qlo[f], qhi[f], qlo[f + 1], qhi[f + 1], khi[f], khi[f + 1]);
    mma1688(a, qml[h], qmh[h], klo[hf]);
    mma1688(c, qml[h], qmh[h], khi[hf]);
    slo[h][0] = a[0];
    slo[h][1] = a[1];
    shi[h][0] = lg[h & 1][0] = far0 ? a[2] : c[2];
    shi[h][1] = lg[h & 1][1] = far1 ? a[3] : c[3];
    if (!ATT_MERGE && (h & 1)) softmax_two(lg, phi[h - 1], phi[h]);
  }
  TSIF(par == 0 && w == 1, 65);
  wg_sync(1 + par);
  TSIF(par == 0 && w == 1, 66);
  const bool nohist = (w == 0) && (b < 8);
  const uint4* hp = g_halo + ((b - 8) * 2 + par) * 224 + lane;
  uint32_t tg[7];
  if (w > 0) {
    const uint4 v0 = lds128(xa + (w - 1) * 2560), v1 = lds128(xa + (w - 1) * 2560 + 512), v2 = lds128(xa + (w - 1) * 2560 + 1024);
    const uint4 v3 = lds128(xa + (w - 1) * 2560 + 1536), v4 = lds128(xa + (w - 1) * 2560 + 2048);
    kpv[0] = v0.x; kpv[1] = v0.y; kpv[2] = v0.z; kpv[3] = v0.w; kpv[4] = v1.x; kpv[5] = v1.y; kpv[6] = v1.z; kpv[7] = v1.w;
    kpv[8] = v2.x; kpv[9] = v2.y; vpv[0] = v2.z; vpv[1] = v2.w; vpv[2] = v3.x; vpv[3] = v3.y; vpv[4] = v3.z; vpv[5] = v3.w;
    vpv[6] = v4.x; vpv[7] = v4.y; vpv[8] = v4.z; vpv[9] = v4.w;
  } else if (nohist) {
#pragma unroll
    for (int j = 0; j < 10; j++) kpv[j] = vpv[j] = 0u;
  } else {
    TSIF(par == 0, 77);
    halo_read(kpv, vpv, tg, hp);
  }
  if (w == 0 && !nohist) {
    int spins = 0;
    while (true) {
      bool ok = true;
#pragma unroll
      for (int j = 0; j < 7; j++) ok = ok && tg[j] == tag;
      if (__all_sync(0xffffffffu, ok) || ++spins > SPIN_LIMIT) break;
      halo_read(kpv, vpv, tg, hp);
    }
    TSIF(par == 0, 79);
  }
#pragma unroll
  for (int h = 0; h < 4; h++) {
    const int f = h == 0 ? 0 : h == 1 ? 3 : h == 2 ? 5 : 8, hf = h < 2 ? 2 : 7;
    float a[4] = {0.f, 0.f, 0.f, 0.f};
    mma16816(a, qlo[f], qhi[f], qlo[f + 1], qhi[f + 1], kpv[f], kpv[f + 1]);
    mma1688(a, qml[h], qmh[h], kpv[hf]);
    const float ninf = __int_as_float(0xff800000);
    lg[h & 1][0] = far0 ? (nohist ? ninf : a[0]) : slo[h][0];
    lg[h & 1][1] = far1 ? (nohist ? ninf : a[1]) : slo[h][1];
    if (h & 1) {
      softmax_two(lg, plo[h - 1], plo[h]);
      if (ATT_MERGE) {
        const float lh[2][2] = {{shi[h - 1][0], shi[h - 1][1]}, {shi[h][0], shi[h][1]}};
        softmax_two(lh, phi[h - 1], phi[h]);
      }
    }
  }
  TSIF(par == 0 && w <= 1, 67 + w);
  uint32_t ov[20];
#pragma unroll
  for (int hp = 0; hp < 2; hp++) {
    const int hf = hp ? 7 : 2;
    float sh[4] = {0.f, 0.f, 0.f, 0.f}, i0 = 0.f, i1 = 0.f;
#pragma unroll
    for (int e = 0; e < 2; e++) {
      const int h = 2 * hp + e, f = h == 0 ? 0 : h == 1 ? 3 : h == 2 ? 5 : 8;
      const uint32_t a0 = plo[h] & mfar, a2 = plo[h] & ~mfar, a3 = phi[h] & mfar, c1 = phi[h] & ~mfar;
      float sum[4] = {0.f, 0.f, 0.f, 0.f};
      mma1688(sum, plo[h], phi[h], 0x3F803F80u);
      const float r0 = rcp(sum[0]), r1 = rcp(sum[2]);
#pragma unroll
      for (int j = f; j < f + 2; j++) {
        float o[4] = {0.f, 0.f, 0.f, 0.f};
        mma16816(o, a0, 0u, a2, a3, vpv[j], vlo[j]);
        mma1688(o, 0u, c1, vhi[j]);
        ov[2 * j] = pack2(o[0] * r0, o[1] * r0);
        ov[2 * j + 1] = pack2(o[2] * r1, o[3] * r1);
      }
      const bool mine = e ? g >= 4 : g < 4;
      mma16816(sh, a0, 0u, a2, a3, mine ? vpv[hf] : 0u, mine ? vlo[hf] : 0u);
      mma1688(sh, 0u, c1, mine ? vhi[hf] : 0u);
      if (e == 0 || t >= 2) {
        i0 = r0;
        i1 = r1;
      }
    }
    ov[2 * hf] = pack2(sh[0] * i0, sh[1] * i0);
    ov[2 * hf + 1] = pack2(sh[2] * i1, sh[3] * i1);
  }
  TS(32 + 4 * par + w);
  mbar_wait(sb + OFF_BAR + 8 * B_P1, 0);
  const uint32_t oa = sb + OFF_OA + (lane >> 4) * 2048 + (32 * w + 2 * (lane & 15) + par) * 16;
#pragma unroll
  for (int j = 0; j < 5; j++) stsm4(oa + 4096 * j, ov + 4 * j);
  TSIF(par == 0 && w == 0, 120);
  fence_async_smem();
  TSIF(par == 0 && w == 0, 121);
  __syncwarp();
  if (lane == 0) mbar_arrive(sb + OFF_BAR + 8 * B_ATTN);
  TSIF(par == 0 && w == 0, 122);
}

struct Maps {
  CUtensorMap x, wm, wt, k, v, y, wo, qm, qt, om, ot, u;
};

__device__ __forceinline__ void load_stage(uint32_t sb, int kb, int b, const Maps& m) {
  const uint32_t st = sb + (kb & 3) * STAGE_BYTES, bar = sb + OFF_BAR + 8 * (B_FULL1 + (kb & 3));
  const int r = b >> 3, hg = b & 7, slab = kb - KV_KB;
  const bool kv = slab >= 0 && slab < 5;
  const uint32_t kbar = sb + OFF_BAR + 8 * (B_KV + slab), dst = sb + OFF_KVS + slab * KVS_BYTES;
  mbar_expect_tx(bar, STAGE_BYTES);
  if (kv) mbar_expect_tx(kbar, KVS_BYTES);
  tma_3d(st, &m.x, 64 * kb, 64 * r, 0, bar);
  if (kv && KV_MIX) tma_3d(dst, &m.k, 0, 32 * (b >> 1) - 3, 2 * slab + (b & 1), kbar);
  tma_3d(st + ST_W, &m.wm, 80 * hg + (tail_first(hg) ? 16 : 0), 64 * kb, 0, bar);
  if (kv && KV_MIX) tma_3d(dst + KVS_V, &m.v, 0, 32 * (b >> 1), 2 * slab + (b & 1), kbar);
  tma_3d(st + ST_WT, &m.wt, 80 * hg + (tail_first(hg) ? 0 : 64), 64 * kb, 0, bar);
  if (kv && !KV_MIX) tma_3d(dst, &m.k, 0, 32 * (b >> 1) - 3, 2 * slab + (b & 1), kbar);
  if (kv && !KV_MIX) tma_3d(dst + KVS_V, &m.v, 0, 32 * (b >> 1), 2 * slab + (b & 1), kbar);
}

__global__ void __launch_bounds__(NTHR, 1) fused_kernel(const __grid_constant__ Maps m, const Params p) {
  extern __shared__ __align__(1024) uint8_t smem[];
  const uint32_t sb = (uint32_t)__cvta_generic_to_shared(smem);
  const uint32_t bars = sb + OFF_BAR;
  const int tid = threadIdx.x, lane = tid & 31;
  int b = blockIdx.x;
  if (BMAP == 1) b = (((b & 63) >> 3) * 2 + (b & 1)) * 8 + (((b < 64 ? 0x6521 : 0x7430) >> (4 * ((b >> 1) & 3))) & 7);
  if (BMAP == 2) b = ((b & 63) >> 2) * 8 + (((b < 64 ? 0x6521 : 0x7430) >> (4 * (b & 3))) & 7);
  if (BMAP == 3) b = (((b & 63) >> 3) * 2 + (b & 1)) * 8 + (((b < 64 ? 0x7430 : 0x6521) >> (4 * ((b >> 1) & 3))) & 7);
  if (BMAP == 4) b = (((b >> 4) * 2 + (b & 1)) * 8) + ((b >> 1) & 7);
  if (BMAP == 5) b = 127 - b;
  const int r = b >> 3, hg = b & 7;

  if (tid == T_ISSUE) {
    TSM(true, 0);
#pragma unroll
    for (int i = 0; i < 4; i++) mbar_init(bars + 8 * (B_FULL1 + i), 1);
#pragma unroll
    for (int i = 0; i < 3; i++) mbar_init(bars + 8 * (B_KV + i), 1);
    fence_async_smem();
#pragma unroll 1
    for (int kb = 0; kb <= PRE2; kb++) load_stage(sb, kb, b, m);
  } else if (tid >= T_PF && tid < T_PF + 12) {
    tm_prefetch(&m.x + (tid - T_PF));
  } else if (tid == T_INIT) {
#pragma unroll
    for (int i = 0; i < 4; i++) mbar_init(bars + 8 * (B_EMPTY1 + i), 8);
#pragma unroll
    for (int i = 0; i < 8; i++) mbar_init(bars + 8 * (B_FULL2 + i), 1);
#pragma unroll
    for (int i = 0; i < 4; i++) mbar_init(bars + 8 * (B_EMPTY2 + i), 8);
#pragma unroll
    for (int i = 0; i < 4; i++) mbar_init(bars + 8 * (B_U + i), 1);
    mbar_init(bars + 8 * B_HA, 4);
    mbar_init(bars + 8 * B_GATE, 4);
    mbar_init(bars + 8 * B_HB, 1);
    mbar_init(bars + 8 * B_KVD, 4);
    mbar_init(bars + 8 * B_QF, 1);
    mbar_init(bars + 8 * B_ATTN, 8);
    mbar_init(bars + 8 * B_P1, 8);
    mbar_init(bars + 8 * B_C34, 1);
#pragma unroll
    for (int i = 0; i < 5; i++) mbar_init(bars + 8 * (B_YST + i), 4);
#pragma unroll
    for (int i = 0; i < 5; i++) mbar_init(bars + 8 * (B_US + i), 4);
    mbar_init(bars + 8 * B_YSIG, 1);
    mbar_init(bars + 8 * B_YFULL, 1);
    mbar_init(bars + 8 * B_EPOCH, 1);
    mbar_init(bars + 8 * B_PREP, 4);
    mbar_init(bars + 8 * B_USIG, 1);
    mbar_init(bars + 8 * B_WST, 1);
#pragma unroll
    for (int i = 3; i < 5; i++) mbar_init(bars + 8 * (B_KV + i), 1);
    mbar_init(bars + 8 * B_E3, 8);
    mbar_init(bars + 8 * B_LAST, 1);
    mbar_init(bars + 8 * B_OSIG, 1);
    mbar_init(bars + 8 * B_WOP, 1);
    fence_async_smem();
  }
  const int warp = __shfl_sync(0xffffffffu, tid >> 5, 0), wg = warp >> 2, w = warp & 3;
  __syncthreads();

  if (wg == 3) {
    asm volatile("setmaxnreg.dec.sync.aligned.u32 56;");
    if (w == 0) {
      if (lane == 0) {
#pragma unroll 1
        for (int kb = 1 + PRE2; kb < 10; kb++) {
          if (kb >= 4) mbar_wait(bars + 8 * (kb == 7 ? B_E3 : B_EMPTY1 + (kb & 3)), (kb >> 3) & 1);
          TSIF(kb >= 4, 44 + kb);
          load_stage(sb, kb, b, m);
          TSIF(kb == 3, 60);
          if (kb == TRIG_KB) mbar_arrive(bars + 8 * B_LAST);
        }
        mbar_wait(bars + 8 * B_WOP, 0);
        mbar_wait(bars + 8 * WL_TRIG, 0);
        mbar_wait(bars + 8 * B_EPOCH, 0);
        flag_wait(g_cnt + C_W + 32 * hg, (lds32(sb + OFF_EPOCH) + 1) * 16);
        TS(30);
#pragma unroll 1
        for (int j = 0; j < 8; j++) {
          if (j >= 6) mbar_wait(bars + 8 * (B_EMPTY2 + j - 6), 0);
          if (j == 4) mbar_wait(bars + 8 * B_ATTN, 0);
          TSIF(j >= 6, 100 + j);
          if (RF_GATE && j == 6) mbar_wait(bars + 8 * B_YSIG, 0);
          mbar_expect_tx(bars + 8 * (B_FULL2 + j), j == 0 ? WO_BYTES : j == 5 ? O_BYTES + WO_BYTES + 512 : O_BYTES + WO_BYTES);
          bulk_load(sb + off_w(j), g_WO + (hg * 8 + step_src(hg, j)) * 800, WO_BYTES, bars + 8 * (B_FULL2 + j));
        }
        mbar_wait(bars + 8 * (B_EMPTY2 + 3), 0);
        mbar_expect_tx(bars + 8 * B_QF, O_BYTES);
        tma_2d(sb + OFF_QS, &m.qm, 80 * hg, 128 * r, bars + 8 * B_QF);
        tma_2d(sb + OFF_QT, &m.qt, 80 * hg + 64, 128 * r, bars + 8 * B_QF);
      }
    } else if (w == 1) {
      unsigned epoch = 0;
      if (lane == 0) {
        epoch = atomicAdd(g_cnt + C_LAUNCH, 1u) / NCTA;
        asm volatile("st.shared.u32 [%0], %1;" ::"r"(sb + OFF_EPOCH), "r"(epoch) : "memory");
        mbar_arrive(bars + 8 * B_EPOCH);
        mbar_wait(bars + 8 * B_KVD, 0);
        mbar_expect_tx(bars + 8 * B_HB, 5 * 4096);
#pragma unroll 1
        for (int c = 0; c < 5; c++) {
          if (c == 3) mbar_wait(bars + 8 * B_S3, 0);
          bulk_load(sb + off_ch(c) + U_BYTES, p.ssm_k + (5 * b + c) * SEQ, 4096, bars + 8 * B_HB);
        }
#pragma unroll
        for (int c = 0; c < 4; c++) mbar_expect_tx(bars + 8 * (B_U + c), c < 3 ? U_BYTES : 2 * U_BYTES);
        const uint4* usrc = g_U + 5 * b * U_PITCH;
        mbar_wait(bars + 8 * B_USIG, 0);
        flag_wait(g_cnt + C_PREP + 32 * (b & 15), (epoch + 1) * NCTA);
        TS(23);
#pragma unroll
        for (int c = 0; c < 5; c++) {
          if (c == 3) mbar_wait(bars + 8 * (B_U + 2), 0);
          bulk_load(sb + off_ch(c), usrc + c * U_PITCH, U_BYTES, bars + 8 * (B_U + (c < 3 ? c : 3)));
          TSIF(c == 0 || c == 4, 116 + (c >> 2));
        }
      }
      epoch = __shfl_sync(0xffffffffu, epoch, 0);
      if (lane < 8) {
        const int src = (b & ~7) | step_src(hg, lane);
        mbar_wait(bars + 8 * B_OSIG, 0);
        TS(20);
        flag_wait(g_cnt + C_O + 32 * src, epoch + 1);
        if (lane >= 1 && lane < 4) bulk_load(sb + off_o(lane), g_O + src * 1280, O_BYTES, bars + 8 * (B_FULL2 + lane));
        __syncwarp(0xff);
        TS(21);
        if (lane == 5) bulk_load(sb + OFF_GATE, g_gate + 128 * r, 512, bars + 8 * (B_FULL2 + 5));
#pragma unroll 1
        for (int j = 4; j < 8; j++) {
          if (lane == j) {
            mbar_wait(bars + 8 * (j < 6 ? B_C34 : B_EMPTY2 + j - 6), 0);
            if (RF_GATE && j == 6) mbar_wait(bars + 8 * B_YSIG, 0);
            bulk_load(sb + off_o(j), g_O + src * 1280, O_BYTES, bars + 8 * (B_FULL2 + j));
          }
          __syncwarp(0xff);
        }
        TS(22);
      }
    } else if (w == 2) {
      mbar_wait(bars + 8 * B_PREP, 0);
      flag_signal(g_cnt + C_PREP, 16, lane);
      TS(25);
      if (lane == 0) mbar_arrive(bars + 8 * B_USIG);
      mbar_wait(bars + 8 * B_GATE, 0);
      if ((NOMB & 1) && lane == 0) asm volatile("fence.release.gpu;" ::: "memory");
      mbar_wait(bars + 8 * B_ATTN, 0);
      if (lane == 0) {
        if (O_DEFER) mbar_wait(bars + 8 * (B_U + 3), 0);
        asm volatile("cp.async.bulk.global.shared::cta.bulk_group [%0], [%1], 20480;\ncp.async.bulk.commit_group;\n"
                     "cp.async.bulk.wait_group 0;\nfence.proxy.async.global;" ::"l"(g_O + b * 1280), "r"(sb + OFF_OA) : "memory");
      }
      TS(74);
      if (!(NOMB & 1)) flag_signal(g_cnt + C_O + 32 * b, 1, lane);
      else if (lane == 0) flag_bump(g_cnt + C_O + 32 * b);
      TS(26);
      if (lane == 0) mbar_arrive(bars + 8 * B_OSIG);

    } else {
      if (lane == 0) {
        uint4* dst = g_WO + (hg * 8 + (r >> 1)) * 800 + (r & 1) * 80;
        mbar_wait(bars + 8 * B_P1, 0);
        mbar_wait(bars + 8 * WB_TRIG, 0);
        mbar_expect_tx(bars + 8 * B_WST, WO_BYTES / 2);
        tma_3d(sb + OFF_WS, &m.wo, 0, 40 * r, 5 * hg, bars + 8 * B_WST);
        mbar_wait(bars + 8 * B_WST, 0);
        mbar_wait(bars + 8 * WO_TRIG, 0);
#pragma unroll 1
        for (int n = 0; n < 5; n++)
          asm volatile("cp.async.bulk.global.shared::cta.bulk_group [%0], [%1], 1280;" ::"l"(dst + 160 * n), "r"(sb + OFF_WS + 1280 * n) : "memory");
        asm volatile("cp.async.bulk.commit_group;\ncp.async.bulk.wait_group 0;\nfence.proxy.async.global;" ::: "memory");
        if (!(NOMB & 4)) asm volatile("fence.release.gpu;" ::: "memory");
        flag_bump(g_cnt + C_W + 32 * hg);
        mbar_arrive(bars + 8 * B_WOP);
        TS(71);
#pragma unroll 1
        for (int c = 0; c < 5; c++) {
          mbar_wait(bars + 8 * (B_YST + c), 0);
          asm volatile("cp.async.bulk.global.shared::cta.bulk_group [%0], [%1], 4096;\ncp.async.bulk.commit_group;"
                       ::"l"(g_Y + (5 * b + c) * Y_PITCH), "r"(sb + off_ch(c)) : "memory");
          if (c == 2) {
            asm volatile("cp.async.bulk.wait_group.read 0;" ::: "memory");
            mbar_arrive(bars + 8 * B_C34);
          }
        }
        asm volatile("cp.async.bulk.wait_group 0;\nfence.proxy.async.global;" ::: "memory");
        TS(75);
        if (!(NOMB & 2)) asm volatile("fence.release.gpu;" ::: "memory");
        flag_bump(g_cnt + C_Y + 32 * (b >> 4));
        TS(27);
        mbar_arrive(bars + 8 * B_YSIG);
        mbar_expect_tx(bars + 8 * B_YFULL, 20480);
        flag_wait(g_cnt + C_Y + 32 * hg, (lds32(sb + OFF_EPOCH) + 1) * 16);
        TS(24);
        tma_2d(sb + OFF_YT, &m.y, 128 * r, 80 * hg, bars + 8 * B_YFULL);
        tma_2d(sb + OFF_YT + 10240, &m.y, 128 * r + 64, 80 * hg, bars + 8 * B_YFULL);
      }
    }
  } else {
    asm volatile("setmaxnreg.inc.sync.aligned.u32 152;");
    if (wg < 2) {
      float acc[120];
#pragma unroll
      for (int i = 0; i < 120; i++) acc[i] = 0.f;
      const uint32_t da = desc_lo(sb + wg * 8192, 16), db = desc_lo(sb + ST_W, 8192), dc = desc_lo(sb + ST_WT, 2048);
      if (PW1) pin<120>(acc);
      if (PW1 == 2) mbar_wait(bars + 8 * B_FULL1, 0);
#pragma unroll 1
      for (int kb = 0; kb < 10; kb++) {
        mbar_wait(bars + 8 * (B_FULL1 + (kb & 3)), (kb >> 2) & 1);
        const uint32_t so = (kb & 3) * (STAGE_BYTES >> 4);
        wg_fence();
#pragma unroll
        for (int k = 0; k < 4; k++) {
          WgSST<192>::mma<HI_SW128, HI_SW128>(acc, da + so + 2 * k, db + so + 128 * k, 1);
          WgSST<48>::mma<HI_SW128, HI_SW32>(acc + 96, da + so + 2 * k, dc + so + 32 * k, 1);
        }
        wg_commit();
        wg_wait<1>();
        if (kb > 0 && lane == 0) mbar_arrive(bars + 8 * (kb == 4 ? B_E3 : B_EMPTY1 + ((kb - 1) & 3)));
      }
      mbar_wait(bars + 8 * B_EPOCH, 0);
      const uint32_t tag = lds32(sb + OFF_EPOCH) + 1;
      mbar_wait(bars + 8 * B_S3, 0);
      wg_wait<0>();
      pin<120>(acc);
      if (lane == 0) mbar_arrive(bars + 8 * B_P1);
      TSM(w == 0, 3 + wg);
      attention(acc, sb, b, wg, w, lane, tag);
    } else {
      const int tw = tid & 127, chl = 64 * (b & 1) + 8 * w + (lane >> 2);
      uint4* up = g_U + chl * U_PITCH + ((4 * (b >> 1) + (lane & 3)) ^ ((b >> 2) & 1));
      uint2 sw[10];
      uint32_t dv = 0;
      if (lane < 5) dv = __ldg(reinterpret_cast<const unsigned short*>(p.ssm_D) + 5 * b + lane);
#pragma unroll
      for (int i = 0; i < 10; i++) sw[i] = ldg64(reinterpret_cast<const uint2*>(p.shift_k) + chl + 128 * (i >> 1) + 32 * (i & 1));
      uint32_t tab[12];
      fft_tables(tab, tw);
      uint4 res[10];
#pragma unroll
      for (int i = 0; i < 10; i++) res[i] = make_uint4(0, 0, 0, 0);
#pragma unroll 1
      for (int slab = 0; slab < 5; slab++) {
#pragma unroll
        for (int i = 0; i < 8; i++) res[i] = res[i + 2];
        prep_slab(res + 8, sw, sb, slab, w, lane);
        TSIF(w == 0, 99 + 4 * slab);
#pragma unroll
        for (int i = 0; i < 8; i++) sw[i] = sw[i + 2];
      }
      TSIF(w == 0, 28);
      __syncwarp();
      if (lane == 0) mbar_arrive(bars + 8 * B_KVD + ((res[8].x ^ res[9].x) & p.zero));
      mbar_wait(bars + 8 * B_KVD, 0);
      fft_tables_store(tab, sb, tw);
      mbar_wait(bars + 8 * B_LAST, 0);
#pragma unroll
      for (int i = 0; i < 10; i++) up[(128 * (i >> 1) + 32 * (i & 1)) * U_PITCH] = res[i];
      __syncwarp();
      if (lane == 0) mbar_arrive(bars + 8 * B_PREP);
      TSIF(w == 0 && !U_TMA, 5);
      mbar_wait(bars + 8 * (G_AFTER ? B_USIG : B_LAST), 0);
      prep_gate(p, b, w, lane);
      __syncwarp();
      if (lane == 0) mbar_arrive(bars + 8 * B_GATE);
      TSIF(w == 0, 72);
      mbar_wait(bars + 8 * B_HB, 0);
      TSIF(w == 0, 123);
      const uint32_t ha = sb + U_BYTES + ((tw >> 3) * 16 + 8 + (tw & 7)) * 16;
      uint4 hv[5];
#pragma unroll
      for (int c = 0; c < 5; c++) hv[c] = lds128(ha + off_ch(c));
      __syncwarp();
#pragma unroll
      for (int c = 0; c < 5; c++) sts128((ha ^ 16) + off_ch(c), hv[c].x, hv[c].y, hv[c].z, hv[c].w);
      if (tw < 5) asm volatile("st.shared.f32 [%0], %1;" ::"r"(sb + OFF_D + 4 * tw), "f"(bf_lo(dv) * 0.125f) : "memory");
      fence_async_smem();
      __syncwarp();
      if (lane == 0) mbar_arrive(bars + 8 * B_HA);
      TSIF(w == 0, 6);
    }

    FftConst fc;
    fft_twiddles(fc, w, lane);
    mbar_wait(bars + 8 * B_HA, 0);
    fft_matrices(fc, sb, w, lane);
    if (ATT_GATE && !H_EARLY) mbar_wait(bars + 8 * B_ATTN, 0);
    TSIF(w == 0 && wg == 2, 124);
#pragma unroll 1
    for (int c = wg == 2 ? 0 : wg + 1; c < 5; c += !CH_W2 ? 3 : wg < 2 ? 5 : c ? 1 : 3) {
      conv_channel(fc, sb, c, wg, w, lane);
      if (lane == 0) mbar_arrive(bars + 8 * (B_YST + c));
      TSM(w == 0, 10 + c);
    }

    if (wg < 2) {
      const int g = lane >> 2;
      float acc[40];
#pragma unroll
      for (int i = 0; i < 40; i++) acc[i] = 0.f;
      const uint32_t da = desc_lo(sb + wg * 1024, 2048), db = desc_lo(sb, 2560);
      mbar_wait(bars + 8 * B_ATTN, 0);
      mbar_wait(bars + 8 * (B_YST + 3), 0);
      mbar_wait(bars + 8 * (B_YST + 4), 0);
      if (PW2) mbar_wait(bars + 8 * B_FULL2, 0);
#pragma unroll 1
      for (int j = 0; j < 8; j++) {
        mbar_wait(bars + 8 * (B_FULL2 + j), 0);
        const uint32_t oa = da + (off_o(j) >> 4), ob = db + (off_w(j) >> 4);
        wg_fence();
#pragma unroll
        for (int k = 0; k < 5; k++) WgSST<80>::mma<HI_NONE, HI_SW32>(acc, oa + 256 * k, ob + 32 * k, 1);
        wg_commit();
        wg_wait<1>();
        if (j >= 1 && j <= 4 && lane == 0) mbar_arrive(bars + 8 * (B_EMPTY2 + j - 1));
      }
      TSIF(w == 0 && wg == 0, 113);
      const int tr = 64 * wg + 16 * w + (lane & 15);
      const uint32_t fm = sb + OFF_QS + tr * 128, fx = (lane >> 4) ^ (tr & 7);
      const uint32_t ft = sb + OFF_QT + tr * 32 + (((lane >> 4) ^ (tr >> 2)) & 1) * 16;
      const float g0 = __uint_as_float(lds32(sb + OFF_GATE + (64 * wg + 16 * w + g) * 4));
      const float g1 = __uint_as_float(lds32(sb + OFF_GATE + (64 * wg + 16 * w + 8 + g) * 4));
      const uint32_t ga = pack2(g0, g0), gb = pack2(g1, g1);
      const uint32_t na = pack2(1.f - g0, 1.f - g0), nb = pack2(1.f - g1, 1.f - g1);

      wg_wait<0>();
      pin<40>(acc);
      TSM(w == 0, 17 + wg);
      uint32_t pb[20];
#pragma unroll
      for (int j = 0; j < 10; j++) {
        pb[2 * j] = bmul(na, pack2(acc[4 * j], acc[4 * j + 1]));
        pb[2 * j + 1] = bmul(nb, pack2(acc[4 * j + 2], acc[4 * j + 3]));
        asm volatile("" : "+r"(pb[2 * j]), "+r"(pb[2 * j + 1]));
      }
      const uint32_t ya = sb + OFF_YT + wg * 10240 + ((lane >> 4) * 8 + (lane & 7)) * 128 +
                          (((2 * w + (((lane >> 3) & 1) ^ wg)) ^ (lane & 7)) << 4);
      uint32_t qf[20];
      mbar_wait(bars + 8 * B_QF, 0);
#pragma unroll
      for (int j = 0; j < 5; j++) ldsm4(qf + 4 * j, j < 4 ? fm + ((fx ^ (2 * j)) << 4) : ft);
      mbar_wait(bars + 8 * B_YFULL, 0);
      TSIF(w == 0 && wg == 0, 19);
#pragma unroll
      for (int j = 0; j < 5; j++) {
        uint32_t y[4];
        ldsm4t(y, ya + 2048 * j);
#pragma unroll
        for (int i = 0; i < 4; i++) qf[4 * j + i] = badd(bmul((i & 1) ? gb : ga, bmul(qf[4 * j + i], y[i])), pb[4 * j + i]);
      }
#pragma unroll
      for (int j = 0; j < 5; j++) stsm4(j < 4 ? fm + ((fx ^ (2 * j)) << 4) : ft, qf + 4 * j);
      fence_async_smem();
      __syncwarp();
      if (lane == 0) {
        const int row = 64 * wg + 16 * w;
        asm volatile("cp.async.bulk.tensor.2d.global.shared::cta.bulk_group [%0, {%2, %3}], [%1];"
                     ::"l"(&m.om), "r"(sb + OFF_QS + row * 128), "r"(80 * hg), "r"(128 * r + row) : "memory");
        asm volatile("cp.async.bulk.tensor.2d.global.shared::cta.bulk_group [%0, {%2, %3}], [%1];"
                     ::"l"(&m.ot), "r"(sb + OFF_QT + row * 32), "r"(80 * hg + 64), "r"(128 * r + row) : "memory");
        asm volatile("cp.async.bulk.commit_group;\ncp.async.bulk.wait_group.read 0;" ::: "memory");
      }
      TSM(true, 40 + 4 * wg + w);
      if (ENDBAR) asm volatile("bar.sync 15, 256;" ::: "memory");
    }
  }
}

typedef CUresult (*EncodeFn)(CUtensorMap*, CUtensorMapDataType, cuuint32_t, void*, const cuuint64_t*, const cuuint64_t*,
                             const cuuint32_t*, const cuuint32_t*, CUtensorMapInterleave, CUtensorMapSwizzle,
                             CUtensorMapL2promotion, CUtensorMapFloatOOBfill);

void encode(EncodeFn fn, CUtensorMap* tm, const void* base, int rank, const cuuint64_t* dims, const cuuint64_t* strides,
            const cuuint32_t* box, CUtensorMapSwizzle swz) {
  const cuuint32_t ones[3] = {1, 1, 1};
  fn(tm, CU_TENSOR_MAP_DATA_TYPE_BFLOAT16, rank, const_cast<void*>(base), dims, strides, box, ones,
     CU_TENSOR_MAP_INTERLEAVE_NONE, swz, CU_TENSOR_MAP_L2_PROMOTION_L2_128B, CU_TENSOR_MAP_FLOAT_OOB_FILL_NONE);
}

}

extern "C" void kernel_launch(void* const* d_in, const int* in_sizes, int n_in, void* d_out, int out_size) {
  (void)in_sizes; (void)n_in; (void)out_size;
  Params p;
  p.q = (const __nv_bfloat16*)d_in[0];
  p.k = (const __nv_bfloat16*)d_in[1];
  p.v = (const __nv_bfloat16*)d_in[2];
  p.shift_k = (const __nv_bfloat16*)d_in[3];
  p.ssm_k = (const __nv_bfloat16*)d_in[4];
  p.ssm_D = (const __nv_bfloat16*)d_in[5];
  p.wqkv = (const __nv_bfloat16*)d_in[7];
  p.wo = (const __nv_bfloat16*)d_in[8];
  p.gate_w = (const __nv_bfloat16*)d_in[9];
  p.out = (__nv_bfloat16*)d_out;
  p.zero = 0;

  static EncodeFn fn = nullptr;
  static void *yaddr = nullptr, *uaddr = nullptr;
  if (!fn) {
    cudaDriverEntryPointQueryResult qr;
    void* f = nullptr;
    cudaGetDriverEntryPoint("cuTensorMapEncodeTiled", &f, cudaEnableDefault, &qr);
    fn = (EncodeFn)f;
    cudaGetSymbolAddress(&yaddr, g_Y);
    cudaGetSymbolAddress(&uaddr, g_U);
    cudaFuncSetAttribute(fused_kernel, cudaFuncAttributeMaxDynamicSharedMemorySize, SMEM_BYTES);
  }
  Maps m;
  {
    const cuuint64_t dims[3] = {640, 1024, 2}, st[2] = {2560, 1280};
    const cuuint32_t box[3] = {64, 64, 2};
    encode(fn, &m.x, p.q, 3, dims, st, box, CU_TENSOR_MAP_SWIZZLE_128B);
  }
  {
    const cuuint64_t dims[3] = {640, 640, 3}, st[2] = {3840, 1280};
    const cuuint32_t box[3] = {64, 64, 3}, boxt[3] = {16, 64, 3};
    encode(fn, &m.wm, p.wqkv, 3, dims, st, box, CU_TENSOR_MAP_SWIZZLE_128B);
    encode(fn, &m.wt, p.wqkv, 3, dims, st, boxt, CU_TENSOR_MAP_SWIZZLE_32B);
  }
  {
    const cuuint64_t dims[3] = {64, 2048, 10}, st[2] = {1280, 128};
    const cuuint32_t boxk[3] = {64, 35, 1}, boxv[3] = {64, 32, 1};
    encode(fn, &m.k, p.k, 3, dims, st, boxk, CU_TENSOR_MAP_SWIZZLE_128B);
    encode(fn, &m.v, p.v, 3, dims, st, boxv, CU_TENSOR_MAP_SWIZZLE_128B);
  }
  {
    const cuuint64_t dims[3] = {16, 640, 40}, st[2] = {1280, 32};
    const cuuint32_t box[3] = {16, 40, 5};
    encode(fn, &m.wo, p.wo, 3, dims, st, box, CU_TENSOR_MAP_SWIZZLE_32B);
  }
  {
    const cuuint64_t dims[2] = {2048, 640}, st[1] = {Y_PITCH * 16};
    const cuuint32_t box[2] = {64, 80};
    encode(fn, &m.y, yaddr, 2, dims, st, box, CU_TENSOR_MAP_SWIZZLE_128B);
    const cuuint64_t stu[1] = {U_PITCH * 16};
    const cuuint32_t boxu[2] = {32, 64};
    encode(fn, &m.u, uaddr, 2, dims, stu, boxu, CU_TENSOR_MAP_SWIZZLE_NONE);
  }
  {
    const cuuint64_t dims[2] = {640, 2048}, st[1] = {1280};
    const cuuint32_t bqm[2] = {64, 128}, bqt[2] = {16, 128}, bom[2] = {64, 16}, bot[2] = {16, 16};
    encode(fn, &m.qm, p.q, 2, dims, st, bqm, CU_TENSOR_MAP_SWIZZLE_128B);
    encode(fn, &m.qt, p.q, 2, dims, st, bqt, CU_TENSOR_MAP_SWIZZLE_32B);
    encode(fn, &m.om, p.out, 2, dims, st, bom, CU_TENSOR_MAP_SWIZZLE_128B);
    encode(fn, &m.ot, p.out, 2, dims, st, bot, CU_TENSOR_MAP_SWIZZLE_32B);
  }
  fused_kernel<<<NCTA, NTHR, SMEM_BYTES>>>(m, p);
}
```

```cpp
#include <cuda.h>
#include <cuda_bf16.h>
#include <cuda_runtime.h>
#include <stdint.h>

namespace {

constexpr int SEQ = 2048, DIM = 640, NCTA = 128, NTHR = 512;

#define TRIG_KB 9
#define KV_KB 2
#define DEV_EXIT 0
#define ATT_GATE 1
#define G_AFTER 0
#define FENCE_LO 0
#define FENCE_HI 0
#define PW1 2
#define PW2 1
#define ENDBAR 0
#define PAD_KB 0
#define Y_ALIAS 1
#define H_EARLY 1
#define NOMB 0
#define SRC_ROT 0
#define WAIT_NS 0
#define WB_TRIG B_USIG
#define G_POS 0
#define TAILF 1
#define T_ISSUE 384
#define T_PF 416
#define T_INIT 448
#define ATT_MERGE 0
#define BMAP 1
#define PRE2 1
#define KV_MIX 0
#define O_DEFER 0
#define CH_W2 0
#define HALO_FIRST 1
#define PREV_EARLY 0
#define PF_KB 1
#define ACQ 0
#define U_TMA 0
#define U_GATE 0
#define RF_GATE 0
#define WO_TRIG B_WST
#define WL_TRIG B_WOP
#define WO_GATE 1

constexpr uint32_t STAGE_BYTES = 47104, ST_W = 16384, ST_WT = 40960;
constexpr uint32_t O_BYTES = 20480, WO_BYTES = 12800;
constexpr uint32_t OFF_OA = 0;
constexpr uint32_t OFF_QS = 3 * O_BYTES, OFF_QT = OFF_QS + 16384;
constexpr uint32_t OFF_WC = 81920;
constexpr uint32_t OFF_WA = 94720;
constexpr uint32_t OFF_GATE = 145920;
constexpr uint32_t OFF_KVX = 147968;
constexpr uint32_t OFF_D = OFF_GATE + 512;
constexpr uint32_t OFF_CH3 = 163840;
constexpr uint32_t CH_BYTES = 12288, U_BYTES = 4096;
constexpr uint32_t OFF_FT = 225280, OFF_GT = 229376;
constexpr uint32_t OFF_CH0 = 188416;
constexpr uint32_t OFF_KVS = OFF_CH0, KVS_V = 4480, KVS_BYTES = 8576;
constexpr uint32_t OFF_WS = OFF_WA;
__device__ __forceinline__ uint32_t off_us(int s) { return OFF_CH0 + 4096 * ((0x65320 >> (4 * s)) & 7); }
constexpr uint32_t OFF_YT = 163840;
constexpr uint32_t OFF_BAR = 231936;
constexpr uint32_t SMEM_BYTES = OFF_BAR + 512;

enum : uint32_t {
  B_FULL1 = 0, B_EMPTY1 = 4, B_S3 = 7, B_FULL2 = 52, B_EMPTY2 = 13, B_U = 8, B_GATE = 12, B_HA = 19, B_HB = 20,
  B_ATTN = 21, B_C34 = 22, B_CONV = 23, B_YFULL = 24, B_EPOCH = 25, B_PREP = 26, B_P1 = 27, B_LAST = 28,
  B_E3 = 29, B_OSIG = 30, B_WOP = 31, B_USIG = 32, B_WST = 33, B_KV = 34, B_KVD = 39, B_HC = 61, B_QF = 62, B_YST = 40,
  B_US = 45, B_YSIG = 50
};
constexpr uint32_t OFF_EPOCH = OFF_BAR + 8 * 51;
__device__ __forceinline__ uint32_t off_o(int j) { return j < 4 ? OFF_OA + j * O_BYTES : j < 6 ? OFF_CH0 + (j - 4) * O_BYTES : OFF_OA + (j - 6) * O_BYTES; }
__device__ __forceinline__ uint32_t off_w(int j) { return j < 4 ? OFF_WA + j * WO_BYTES : j == 4 ? OFF_KVX : j == 5 ? OFF_WC : OFF_WA + (j - 6) * WO_BYTES; }
__device__ __forceinline__ int step_src(int hg, int j) { return SRC_ROT ? (hg + j) & 7 : j == 0 ? hg : j <= hg ? j - 1 : j; }
__device__ __forceinline__ bool tail_first(int hg) { return TAILF && (hg & 3) == 3; }
__device__ __forceinline__ uint32_t off_ch(int c) { return (c < 3 ? OFF_CH0 : OFF_CH3 - 3 * CH_BYTES) + c * CH_BYTES; }

#define U_PITCH 264
__device__ __align__(1024) uint4 g_U[DIM * U_PITCH];
__device__ uint4 g_O[NCTA * 1280];
#define g_Y g_U
constexpr int Y_PITCH = U_PITCH;
__device__ uint4 g_WO[64 * 800];
__device__ uint4 g_halo[NCTA * 2 * 7 * 32];
__device__ float g_gate[SEQ + PAD_KB * 256];
__device__ unsigned g_cnt[32 * (1 + 2 * 16 + 8 + NCTA)];
constexpr int C_LAUNCH = 0, C_PREP = 32, C_Y = 32 * 17, C_W = 32 * 33, C_O = 32 * 41;

#define TSM(cond, slot) do { } while (0)
#define TSIF(cond, slot) do { if (__LINE__ >= FENCE_LO && __LINE__ < FENCE_HI) sched_fence(); } while (0)
__device__ __forceinline__ void sched_fence() {
  asm volatile("{\n.reg .pred p;\n.reg .u32 c;\nmov.u32 c, %%clock;\nsetp.eq.u32 p, c, 0;\n@p st.shared.u32 [%0], c;\n}"
               ::"r"(1024 + OFF_EPOCH + 4) : "memory");
}
#define TS(slot) TSIF(true, slot)

struct Params {
  const __nv_bfloat16 *q, *k, *v, *shift_k, *ssm_k, *ssm_D, *wqkv, *wo, *gate_w;
  __nv_bfloat16* out;
  uint32_t zero;
};

#define POLL_NS 0
constexpr int SPIN_LIMIT = 1 << 17;

__device__ __forceinline__ void mbar_init(uint32_t bar, uint32_t count) {
  asm volatile("mbarrier.init.shared::cta.b64 [%0], %1;" ::"r"(bar), "r"(count) : "memory");
}
__device__ __forceinline__ void mbar_expect_tx(uint32_t bar, uint32_t bytes) {
  asm volatile("mbarrier.arrive.expect_tx.shared::cta.b64 _, [%0], %1;" ::"r"(bar), "r"(bytes) : "memory");
}
__device__ __forceinline__ void mbar_arrive(uint32_t bar) {
  asm volatile("mbarrier.arrive.shared::cta.b64 _, [%0];" ::"r"(bar) : "memory");
}
__device__ __forceinline__ void mbar_wait(uint32_t bar, uint32_t parity) {
  uint32_t ok;
  int spins = 0;
  do {
    if (WAIT_NS)
      asm volatile("{\n.reg .pred p;\nmbarrier.try_wait.parity.shared::cta.b64 p, [%1], %2, %3;\nselp.b32 %0, 1, 0, p;\n}"
                   : "=r"(ok) : "r"(bar), "r"(parity), "r"(WAIT_NS) : "memory");
    else
      asm volatile("{\n.reg .pred p;\nmbarrier.try_wait.parity.shared::cta.b64 p, [%1], %2;\nselp.b32 %0, 1, 0, p;\n}"
                   : "=r"(ok) : "r"(bar), "r"(parity) : "memory");
    if (++spins > SPIN_LIMIT) break;
  } while (!ok);
}
__device__ __forceinline__ void flag_poll(const unsigned* p, unsigned target) {
  unsigned v;
  int spins = 0;
  do {
    if (POLL_NS && spins) __nanosleep(POLL_NS);
    asm volatile("ld.relaxed.gpu.global.u32 %0, [%1];" : "=r"(v) : "l"(p) : "memory");
    if (++spins > SPIN_LIMIT) break;
  } while ((int)(v - target) < 0);
}
__device__ __forceinline__ void flag_wait(const unsigned* p, unsigned target) {
  flag_poll(p, target);
  if (ACQ) asm volatile("fence.acquire.gpu;\nfence.proxy.async.global;" ::: "memory");
}
__device__ __forceinline__ void flag_signal(unsigned* p, int n, int lane) {
  if (lane == 0) asm volatile("fence.release.gpu;" ::: "memory");
  __syncwarp();
  if (lane < n) asm volatile("red.relaxed.gpu.global.add.u32 [%0], 1;" ::"l"(p + 32 * lane) : "memory");
}
__device__ __forceinline__ void flag_bump(unsigned* p) {
  asm volatile("red.relaxed.gpu.global.add.u32 [%0], 1;" ::"l"(p) : "memory");
}
__device__ __forceinline__ void fence_async_smem() { asm volatile("fence.proxy.async.shared::cta;" ::: "memory"); }
__device__ __forceinline__ void wg_sync(int id) { asm volatile("bar.sync %0, 128;" ::"r"(id) : "memory"); }

__device__ __forceinline__ void tma_2d(uint32_t dst, const CUtensorMap* tm, int c0, int c1, uint32_t bar) {
  asm volatile("cp.async.bulk.tensor.2d.shared::cluster.global.mbarrier::complete_tx::bytes [%0], [%1, {%3, %4}], [%2];"
               ::"r"(dst), "l"(tm), "r"(bar), "r"(c0), "r"(c1) : "memory");
}
__device__ __forceinline__ void tma_3d(uint32_t dst, const CUtensorMap* tm, int c0, int c1, int c2, uint32_t bar) {
  asm volatile("cp.async.bulk.tensor.3d.shared::cluster.global.mbarrier::complete_tx::bytes [%0], [%1, {%3, %4, %5}], [%2];"
               ::"r"(dst), "l"(tm), "r"(bar), "r"(c0), "r"(c1), "r"(c2) : "memory");
}
__device__ __forceinline__ void bulk_load(uint32_t dst, const void* src, uint32_t bytes, uint32_t bar) {
  asm volatile("cp.async.bulk.shared::cluster.global.mbarrier::complete_tx::bytes [%0], [%1], %2, [%3];"
               ::"r"(dst), "l"(src), "r"(bytes), "r"(bar) : "memory");
}
__device__ __forceinline__ void tm_prefetch(const CUtensorMap* tm) {
  asm volatile("prefetch.tensormap [%0];" ::"l"(tm) : "memory");
}

__device__ __forceinline__ void wg_fence() { asm volatile("wgmma.fence.sync.aligned;" ::: "memory"); }
__device__ __forceinline__ void wg_commit() { asm volatile("wgmma.commit_group.sync.aligned;" ::: "memory"); }
template <int N> __device__ __forceinline__ void wg_wait() { asm volatile("wgmma.wait_group.sync.aligned %0;" ::"n"(N) : "memory"); }
__device__ __forceinline__ uint32_t desc_lo(uint32_t addr, uint32_t lbo) { return ((addr & 0x3FFFF) >> 4) | ((lbo >> 4) << 16); }
constexpr uint32_t desc_hi(uint32_t sbo, uint32_t swz) { return (sbo >> 4) | (swz << 30); }
constexpr uint32_t HI_SW128 = desc_hi(1024, 1), HI_SW64 = desc_hi(512, 2), HI_SW32 = desc_hi(256, 3), HI_NONE = desc_hi(128, 0);
template <int N> __device__ __forceinline__ void pin(float* d) {
#pragma unroll
  for (int i = 0; i < N; i++) asm volatile("" : "+f"(d[i])::"memory");
}

__device__ __forceinline__ uint32_t lds32(uint32_t a) {
  uint32_t v;
  asm volatile("ld.volatile.shared.u32 %0, [%1];" : "=r"(v) : "r"(a) : "memory");
  return v;
}
__device__ __forceinline__ uint4 ldg128(const void* a) {
  uint4 v;
  asm volatile("ld.global.nc.v4.u32 {%0, %1, %2, %3}, [%4];" : "=r"(v.x), "=r"(v.y), "=r"(v.z), "=r"(v.w) : "l"(a) : "memory");
  return v;
}
__device__ __forceinline__ uint2 ldg64(const void* a) {
  uint2 v;
  asm volatile("ld.global.nc.v2.u32 {%0, %1}, [%2];" : "=r"(v.x), "=r"(v.y) : "l"(a) : "memory");
  return v;
}
__device__ __forceinline__ void ldsm4(uint32_t* r, uint32_t a) {
  asm volatile("ldmatrix.sync.aligned.m8n8.x4.shared.b16 {%0, %1, %2, %3}, [%4];"
               : "=r"(r[0]), "=r"(r[1]), "=r"(r[2]), "=r"(r[3]) : "r"(a) : "memory");
}
__device__ __forceinline__ void ldsm4t(uint32_t* r, uint32_t a) {
  asm volatile("ldmatrix.sync.aligned.m8n8.x4.trans.shared.b16 {%0, %1, %2, %3}, [%4];"
               : "=r"(r[0]), "=r"(r[1]), "=r"(r[2]), "=r"(r[3]) : "r"(a) : "memory");
}
__device__ __forceinline__ uint4 lds128(uint32_t a) {
  uint4 v;
  asm volatile("ld.shared.v4.u32 {%0, %1, %2, %3}, [%4];" : "=r"(v.x), "=r"(v.y), "=r"(v.z), "=r"(v.w) : "r"(a) : "memory");
  return v;
}
__device__ __forceinline__ void sts128(uint32_t a, uint32_t x, uint32_t y, uint32_t z, uint32_t w) {
  asm volatile("st.shared.v4.u32 [%0], {%1, %2, %3, %4};" ::"r"(a), "r"(x), "r"(y), "r"(z), "r"(w) : "memory");
}
__device__ __forceinline__ void stsm4(uint32_t a, const uint32_t* r) {
  asm volatile("stmatrix.sync.aligned.m8n8.x4.shared.b16 [%0], {%1, %2, %3, %4};" ::"r"(a), "r"(r[0]), "r"(r[1]), "r"(r[2]), "r"(r[3]) : "memory");
}
__device__ __forceinline__ void stsm4t(uint32_t a, const uint32_t* r) {
  asm volatile("stmatrix.sync.aligned.m8n8.x4.trans.shared.b16 [%0], {%1, %2, %3, %4};" ::"r"(a), "r"(r[0]), "r"(r[1]), "r"(r[2]), "r"(r[3]) : "memory");
}
__device__ __forceinline__ uint32_t pack2(float lo, float hi) {
  uint32_t r;
  asm("cvt.rn.bf16x2.f32 %0, %1, %2;" : "=r"(r) : "f"(hi), "f"(lo));
  return r;
}
__device__ __forceinline__ uint32_t movm(uint32_t a) {
  uint32_t d;
  asm volatile("movmatrix.sync.aligned.m8n8.trans.b16 %0, %1;" : "=r"(d) : "r"(a));
  return d;
}
__device__ __forceinline__ uint32_t bmul(uint32_t a, uint32_t b) {
  uint32_t d;
  asm("mul.rn.bf16x2 %0, %1, %2;" : "=r"(d) : "r"(a), "r"(b));
  return d;
}
__device__ __forceinline__ uint32_t badd(uint32_t a, uint32_t b) {
  uint32_t d;
  asm("add.rn.bf16x2 %0, %1, %2;" : "=r"(d) : "r"(a), "r"(b));
  return d;
}
__device__ __forceinline__ float bf_lo(uint32_t x) { return __uint_as_float(x << 16); }
__device__ __forceinline__ float bf_hi(uint32_t x) { return __uint_as_float(x & 0xFFFF0000u); }
__device__ __forceinline__ float ex2(float x) {
  float y;
  asm("ex2.approx.ftz.f32 %0, %1;" : "=f"(y) : "f"(x));
  return y;
}
__device__ __forceinline__ float rcp(float x) {
  float y;
  asm("rcp.approx.ftz.f32 %0, %1;" : "=f"(y) : "f"(x));
  return y;
}
__device__ __forceinline__ void mma16816(float* d, uint32_t a0, uint32_t a1, uint32_t a2, uint32_t a3, uint32_t b0, uint32_t b1) {
  asm volatile("mma.sync.aligned.m16n8k16.row.col.f32.bf16.bf16.f32 {%0, %1, %2, %3}, {%4, %5, %6, %7}, {%8, %9}, {%0, %1, %2, %3};"
               : "+f"(d[0]), "+f"(d[1]), "+f"(d[2]), "+f"(d[3])
               : "r"(a0), "r"(a1), "r"(a2), "r"(a3), "r"(b0), "r"(b1));
}
__device__ __forceinline__ void mma1688(float* d, uint32_t a0, uint32_t a1, uint32_t b0) {
  asm volatile("mma.sync.aligned.m16n8k8.row.col.f32.bf16.bf16.f32 {%0, %1, %2, %3}, {%4, %5}, {%6}, {%0, %1, %2, %3};"
               : "+f"(d[0]), "+f"(d[1]), "+f"(d[2]), "+f"(d[3])
               : "r"(a0), "r"(a1), "r"(b0));
}

template <int N> struct WgRS;
template <int N> struct WgSST;
template <> struct WgRS<32> {
  template <uint32_t HB>
  static __device__ __forceinline__ void mma(float* d, const uint32_t* a, uint32_t db) {
    asm volatile("{\n.reg .pred p;\n.reg .b64 db;\nsetp.ne.b32 p, %22, 0;\n"
      "mov.b64 db, {%20, %21};\n"
      "wgmma.mma_async.sync.aligned.m64n32k16.f32.bf16.bf16 {"
      "%0, %1, %2, %3, %4, %5, %6, %7, %8, %9, %10, %11, %12, %13, %14, %15"
      "}, {%16, %17, %18, %19}, db, p, 1, 1, 1;\n}\n"
      : "+f"(d[0]), "+f"(d[1]), "+f"(d[2]), "+f"(d[3]), "+f"(d[4]), "+f"(d[5]), "+f"(d[6]), "+f"(d[7]),
        "+f"(d[8]), "+f"(d[9]), "+f"(d[10]), "+f"(d[11]), "+f"(d[12]), "+f"(d[13]), "+f"(d[14]), "+f"(d[15])
      : "r"(a[0]), "r"(a[1]), "r"(a[2]), "r"(a[3]), "r"(db), "n"(HB), "n"(1));
  }
  template <uint32_t HB>
  static __device__ __forceinline__ void set(float* d, const uint32_t* a, uint32_t db) {
    asm volatile("{\n.reg .pred p;\n.reg .b64 db;\nsetp.ne.b32 p, %22, 0;\n"
      "mov.b64 db, {%20, %21};\n"
      "wgmma.mma_async.sync.aligned.m64n32k16.f32.bf16.bf16 {"
      "%0, %1, %2, %3, %4, %5, %6, %7, %8, %9, %10, %11, %12, %13, %14, %15"
      "}, {%16, %17, %18, %19}, db, p, 1, 1, 1;\n}\n"
      : "=f"(d[0]), "=f"(d[1]), "=f"(d[2]), "=f"(d[3]), "=f"(d[4]), "=f"(d[5]), "=f"(d[6]), "=f"(d[7]),
        "=f"(d[8]), "=f"(d[9]), "=f"(d[10]), "=f"(d[11]), "=f"(d[12]), "=f"(d[13]), "=f"(d[14]), "=f"(d[15])
      : "r"(a[0]), "r"(a[1]), "r"(a[2]), "r"(a[3]), "r"(db), "n"(HB), "n"(0));
  }
};
template <> struct WgRS<64> {
  template <uint32_t HB>
  static __device__ __forceinline__ void mma(float* d, const uint32_t* a, uint32_t db) {
    asm volatile("{\n.reg .pred p;\n.reg .b64 db;\nsetp.ne.b32 p, %38, 0;\n"
      "mov.b64 db, {%36, %37};\n"
      "wgmma.mma_async.sync.aligned.m64n64k16.f32.bf16.bf16 {"
      "%0, %1, %2, %3, %4, %5, %6, %7, %8, %9, %10, %11, %12, %13, %14, %15, "
      "%16, %17, %18, %19, %20, %21, %22, %23, %24, %25, %26, %27, %28, %29, %30, %31"
      "}, {%32, %33, %34, %35}, db, p, 1, 1, 1;\n}\n"
      : "+f"(d[0]), "+f"(d[1]), "+f"(d[2]), "+f"(d[3]), "+f"(d[4]), "+f"(d[5]), "+f"(d[6]), "+f"(d[7]),
        "+f"(d[8]), "+f"(d[9]), "+f"(d[10]), "+f"(d[11]), "+f"(d[12]), "+f"(d[13]), "+f"(d[14]), "+f"(d[15]),
        "+f"(d[16]), "+f"(d[17]), "+f"(d[18]), "+f"(d[19]), "+f"(d[20]), "+f"(d[21]), "+f"(d[22]), "+f"(d[23]),
        "+f"(d[24]), "+f"(d[25]), "+f"(d[26]), "+f"(d[27]), "+f"(d[28]), "+f"(d[29]), "+f"(d[30]), "+f"(d[31])
      : "r"(a[0]), "r"(a[1]), "r"(a[2]), "r"(a[3]), "r"(db), "n"(HB), "n"(1));
  }
  template <uint32_t HB>
  static __device__ __forceinline__ void set(float* d, const uint32_t* a, uint32_t db) {
    asm volatile("{\n.reg .pred p;\n.reg .b64 db;\nsetp.ne.b32 p, %38, 0;\n"
      "mov.b64 db, {%36, %37};\n"
      "wgmma.mma_async.sync.aligned.m64n64k16.f32.bf16.bf16 {"
      "%0, %1, %2, %3, %4, %5, %6, %7, %8, %9, %10, %11, %12, %13, %14, %15, "
      "%16, %17, %18, %19, %20, %21, %22, %23, %24, %25, %26, %27, %28, %29, %30, %31"
      "}, {%32, %33, %34, %35}, db, p, 1, 1, 1;\n}\n"
      : "=f"(d[0]), "=f"(d[1]), "=f"(d[2]), "=f"(d[3]), "=f"(d[4]), "=f"(d[5]), "=f"(d[6]), "=f"(d[7]),
        "=f"(d[8]), "=f"(d[9]), "=f"(d[10]), "=f"(d[11]), "=f"(d[12]), "=f"(d[13]), "=f"(d[14]), "=f"(d[15]),
        "=f"(d[16]), "=f"(d[17]), "=f"(d[18]), "=f"(d[19]), "=f"(d[20]), "=f"(d[21]), "=f"(d[22]), "=f"(d[23]),
        "=f"(d[24]), "=f"(d[25]), "=f"(d[26]), "=f"(d[27]), "=f"(d[28]), "=f"(d[29]), "=f"(d[30]), "=f"(d[31])
      : "r"(a[0]), "r"(a[1]), "r"(a[2]), "r"(a[3]), "r"(db), "n"(HB), "n"(0));
  }
};
template <> struct WgSST<48> {
  template <uint32_t HA, uint32_t HB>
  static __device__ __forceinline__ void mma(float* d, uint32_t da, uint32_t db, int sc) {
    asm volatile("{\n.reg .pred p;\n.reg .b64 da, db;\nsetp.ne.b32 p, %28, 0;\n"
      "mov.b64 da, {%24, %25};\nmov.b64 db, {%26, %27};\n"
      "wgmma.mma_async.sync.aligned.m64n48k16.f32.bf16.bf16 {"
      "%0, %1, %2, %3, %4, %5, %6, %7, %8, %9, %10, %11, %12, %13, %14, %15, "
      "%16, %17, %18, %19, %20, %21, %22, %23"
      "}, da, db, p, 1, 1, 0, 1;\n}\n"
      : "+f"(d[0]), "+f"(d[1]), "+f"(d[2]), "+f"(d[3]), "+f"(d[4]), "+f"(d[5]), "+f"(d[6]), "+f"(d[7]),
        "+f"(d[8]), "+f"(d[9]), "+f"(d[10]), "+f"(d[11]), "+f"(d[12]), "+f"(d[13]), "+f"(d[14]), "+f"(d[15]),
        "+f"(d[16]), "+f"(d[17]), "+f"(d[18]), "+f"(d[19]), "+f"(d[20]), "+f"(d[21]), "+f"(d[22]), "+f"(d[23])
      : "r"(da), "n"(HA), "r"(db), "n"(HB), "r"(sc));
  }
};
template <> struct WgSST<80> {
  template <uint32_t HA, uint32_t HB>
  static __device__ __forceinline__ void mma(float* d, uint32_t da, uint32_t db, int sc) {
    asm volatile("{\n.reg .pred p;\n.reg .b64 da, db;\nsetp.ne.b32 p, %44, 0;\n"
      "mov.b64 da, {%40, %41};\nmov.b64 db, {%42, %43};\n"
      "wgmma.mma_async.sync.aligned.m64n80k16.f32.bf16.bf16 {"
      "%0, %1, %2, %3, %4, %5, %6, %7, %8, %9, %10, %11, %12, %13, %14, %15, "
      "%16, %17, %18, %19, %20, %21, %22, %23, %24, %25, %26, %27, %28, %29, %30, %31, "
      "%32, %33, %34, %35, %36, %37, %38, %39"
      "}, da, db, p, 1, 1, 0, 1;\n}\n"
      : "+f"(d[0]), "+f"(d[1]), "+f"(d[2]), "+f"(d[3]), "+f"(d[4]), "+f"(d[5]), "+f"(d[6]), "+f"(d[7]),
        "+f"(d[8]), "+f"(d[9]), "+f"(d[10]), "+f"(d[11]), "+f"(d[12]), "+f"(d[13]), "+f"(d[14]), "+f"(d[15]),
        "+f"(d[16]), "+f"(d[17]), "+f"(d[18]), "+f"(d[19]), "+f"(d[20]), "+f"(d[21]), "+f"(d[22]), "+f"(d[23]),
        "+f"(d[24]), "+f"(d[25]), "+f"(d[26]), "+f"(d[27]), "+f"(d[28]), "+f"(d[29]), "+f"(d[30]), "+f"(d[31]),
        "+f"(d[32]), "+f"(d[33]), "+f"(d[34]), "+f"(d[35]), "+f"(d[36]), "+f"(d[37]), "+f"(d[38]), "+f"(d[39])
      : "r"(da), "n"(HA), "r"(db), "n"(HB), "r"(sc));
  }
};
template <> struct WgSST<192> {
  template <uint32_t HA, uint32_t HB>
  static __device__ __forceinline__ void mma(float* d, uint32_t da, uint32_t db, int sc) {
    asm volatile("{\n.reg .pred p;\n.reg .b64 da, db;\nsetp.ne.b32 p, %100, 0;\n"
      "mov.b64 da, {%96, %97};\nmov.b64 db, {%98, %99};\n"
      "wgmma.mma_async.sync.aligned.m64n192k16.f32.bf16.bf16 {"
      "%0, %1, %2, %3, %4, %5, %6, %7, %8, %9, %10, %11, %12, %13, %14, %15, "
      "%16, %17, %18, %19, %20, %21, %22, %23, %24, %25, %26, %27, %28, %29, %30, %31, "
      "%32, %33, %34, %35, %36, %37, %38, %39, %40, %41, %42, %43, %44, %45, %46, %47, "
      "%48, %49, %50, %51, %52, %53, %54, %55, %56, %57, %58, %59, %60, %61, %62, %63, "
      "%64, %65, %66, %67, %68, %69, %70, %71, %72, %73, %74, %75, %76, %77, %78, %79, "
      "%80, %81, %82, %83, %84, %85, %86, %87, %88, %89, %90, %91, %92, %93, %94, %95"
      "}, da, db, p, 1, 1, 0, 1;\n}\n"
      : "+f"(d[0]), "+f"(d[1]), "+f"(d[2]), "+f"(d[3]), "+f"(d[4]), "+f"(d[5]), "+f"(d[6]), "+f"(d[7]),
        "+f"(d[8]), "+f"(d[9]), "+f"(d[10]), "+f"(d[11]), "+f"(d[12]), "+f"(d[13]), "+f"(d[14]), "+f"(d[15]),
        "+f"(d[16]), "+f"(d[17]), "+f"(d[18]), "+f"(d[19]), "+f"(d[20]), "+f"(d[21]), "+f"(d[22]), "+f"(d[23]),
        "+f"(d[24]), "+f"(d[25]), "+f"(d[26]), "+f"(d[27]), "+f"(d[28]), "+f"(d[29]), "+f"(d[30]), "+f"(d[31]),
        "+f"(d[32]), "+f"(d[33]), "+f"(d[34]), "+f"(d[35]), "+f"(d[36]), "+f"(d[37]), "+f"(d[38]), "+f"(d[39]),
        "+f"(d[40]), "+f"(d[41]), "+f"(d[42]), "+f"(d[43]), "+f"(d[44]), "+f"(d[45]), "+f"(d[46]), "+f"(d[47]),
        "+f"(d[48]), "+f"(d[49]), "+f"(d[50]), "+f"(d[51]), "+f"(d[52]), "+f"(d[53]), "+f"(d[54]), "+f"(d[55]),
        "+f"(d[56]), "+f"(d[57]), "+f"(d[58]), "+f"(d[59]), "+f"(d[60]), "+f"(d[61]), "+f"(d[62]), "+f"(d[63]),
        "+f"(d[64]), "+f"(d[65]), "+f"(d[66]), "+f"(d[67]), "+f"(d[68]), "+f"(d[69]), "+f"(d[70]), "+f"(d[71]),
        "+f"(d[72]), "+f"(d[73]), "+f"(d[74]), "+f"(d[75]), "+f"(d[76]), "+f"(d[77]), "+f"(d[78]), "+f"(d[79]),
        "+f"(d[80]), "+f"(d[81]), "+f"(d[82]), "+f"(d[83]), "+f"(d[84]), "+f"(d[85]), "+f"(d[86]), "+f"(d[87]),
        "+f"(d[88]), "+f"(d[89]), "+f"(d[90]), "+f"(d[91]), "+f"(d[92]), "+f"(d[93]), "+f"(d[94]), "+f"(d[95])
      : "r"(da), "n"(HA), "r"(db), "n"(HB), "r"(sc));
  }
};

struct FftConst {
  uint32_t f[2][4], fi[4][4];
  float ta[4], tb[4];
};
__device__ __forceinline__ void cis(int m, float scale, float& c, float& s) {
  const float a = (float)m * (-6.283185307179586f * scale);
  c = __cosf(a);
  s = __sinf(a);
}
__device__ __forceinline__ void fft_tables(uint32_t (&v)[12], int tw) {
  const int row = tw >> 2, ch = tw & 3;
#pragma unroll
  for (int i = 0; i < 4; i++) {
    float c[2], s[2], x[2];
#pragma unroll
    for (int e = 0; e < 2; e++) {
      cis((((32 * (8 * ch + 2 * i + e) + 15) * (4 * row - 63) + 2048) & 4095) - 2048, 1.f / 4096, c[e], s[e]);
      float gc, gs;
      cis((((row & 15) * (8 * (ch & 1) + 2 * i + e) + 8) & 15) - 8, 1.f / 16, gc, gs);
      x[e] = (row >> 4) == (ch >> 1) ? gc : (ch >> 1) ? gs : -gs;
    }
    v[i] = pack2(c[0] * 0.125f, c[1] * 0.125f);
    v[4 + i] = pack2(s[0] * 0.125f, s[1] * 0.125f);
    v[8 + i] = pack2(x[0], x[1]);
  }
#pragma unroll
  for (int i = 0; i < 12; i++) asm volatile("" : "+r"(v[i]));
}
__device__ __forceinline__ void fft_tables_store(const uint32_t (&v)[12], uint32_t sb, int tw) {
  const int row = tw >> 2;
  const uint32_t x = ((tw ^ (row >> 1)) & 3) << 4, a = sb + OFF_FT + (16 * (row >> 3) + (row & 7)) * 64 + x;
  sts128(a, v[0], v[1], v[2], v[3]);
  sts128(a + 512, v[4], v[5], v[6], v[7]);
  sts128(sb + OFF_GT + row * 64 + x, v[8], v[9], v[10], v[11]);
}
__device__ __forceinline__ void fft_twiddles(FftConst& k, int w, int lane) {
#pragma unroll
  for (int i = 0; i < 4; i++) {
    float c, s;
    cis((2 * (8 * (i >> 1) + 2 * (lane & 3) + (i & 1)) - 15) * (4 * (8 * w + (lane >> 2)) - 63), 1.f / 4096, c, s);
    k.ta[i] = __fdividef(-s, 1.f + c);
    k.tb[i] = s;
  }
  pin<4>(k.ta);
  pin<4>(k.tb);
}
__device__ __forceinline__ void fft_matrices(FftConst& k, uint32_t sb, int w, int lane) {
  const uint32_t x = (lane >> 1) & 3;
#pragma unroll
  for (int i = 0; i < 2; i++) {
    ldsm4(k.f[i], sb + OFF_FT + (16 * w + (lane & 15)) * 64 + (((2 * i + (lane >> 4)) ^ x) << 4));
    ldsm4t(k.fi[i], sb + OFF_FT + (32 * i + lane) * 64 + ((w ^ x) << 4));
#pragma unroll
    for (int j = 0; j < 4; j++) {
      k.fi[2 + i][j] = (j & 1) ? k.fi[i][j - 1] ^ 0x80008000u : k.fi[i][j + 1];
      asm volatile("" : "+r"(k.fi[2 + i][j]));
    }
  }
}
template <bool INV> __device__ __forceinline__ void rot(float& x, float& y, float a, float b) {
  x = fmaf(INV ? -a : a, y, x);
  y = fmaf(INV ? -b : b, x, y);
  x = fmaf(INV ? -a : a, y, x);
}
__device__ __forceinline__ void twiddle_fwd(uint32_t (&a)[4][4], float* d, const FftConst& k) {
#pragma unroll
  for (int q = 0; q < 4; q++)
#pragma unroll
    for (int j = 0; j < 2; j++) {
      float* x = d + 8 * q + 4 * j;
      rot<false>(x[0], x[2], k.ta[2 * j], k.tb[2 * j]);
      rot<false>(x[1], x[3], k.ta[2 * j + 1], k.tb[2 * j + 1]);
      a[q & 2][2 * j + (q & 1)] = pack2(x[0], x[1]);
      a[(q & 2) + 1][2 * j + (q & 1)] = pack2(x[2], x[3]);
    }
}
__device__ __forceinline__ void g_step(float* d, const uint32_t (&a)[4][4], uint32_t dre, uint32_t dim) {
  WgRS<32>::set<HI_SW64>(d, a[0], dre);
  WgRS<32>::set<HI_SW64>(d + 16, a[2], dre);
  WgRS<32>::mma<HI_SW64>(d, a[1], dim);
  WgRS<32>::mma<HI_SW64>(d + 16, a[3], dim);
  wg_commit();
}

__device__ __forceinline__ void conv_channel(const FftConst& k, uint32_t sb, int c, int wg, int w, int lane) {
  const uint32_t cb = sb + off_ch(c), bars = sb + OFF_BAR;
  const uint32_t du = desc_lo(cb, 1024), dg = desc_lo(sb + OFF_GT, 16), dz = desc_lo(cb + U_BYTES, 16);
  float U[32], H[32];
  uint32_t a[4][4], e[4][4];
  const float dv = __uint_as_float(lds32(sb + OFF_D + 4 * c));
  wg_fence();
  WgRS<64>::set<HI_SW32>(H, k.f[0], du + 256);
  WgRS<64>::mma<HI_SW32>(H, k.f[1], du + 256 + 32);
  wg_commit();
  wg_wait<0>();
  pin<32>(H);
  twiddle_fwd(a, H, k);
  if (ATT_GATE && H_EARLY) mbar_wait(bars + 8 * B_ATTN, 0);
  mbar_wait(bars + 8 * (B_U + (c < 3 ? c : 3)), 0);
  TSM(w == 0 && c < 3, 7 + wg);
  wg_fence();
  WgRS<64>::set<HI_SW32>(U, k.f[0], du);
  WgRS<64>::mma<HI_SW32>(U, k.f[1], du + 32);
  wg_commit();
  g_step(H, a, dg, dg + 64);
  wg_wait<1>();
  pin<32>(U);
  twiddle_fwd(e, U, k);
  wg_fence();
  g_step(U, e, dg, dg + 64);
  wg_wait<0>();
  pin<32>(U);
  pin<32>(H);
#pragma unroll
  for (int j = 0; j < 2; j++) {
    float pr[4][2], pi[4][2];
#pragma unroll
    for (int x = 0; x < 2; x++) {
      H[4 * j + x] += dv;
#pragma unroll
      for (int m = 0; m < 4; m++) {
#pragma unroll
        for (int q = 0; q <= m; q++) {
          const int ih = 16 * (q >> 1) + 2 * (q & 1) + 4 * j + x, iu = 16 * ((m - q) >> 1) + 2 * ((m - q) & 1) + 4 * j + x;
          pr[m][x] = q ? fmaf(H[ih], U[iu], pr[m][x]) : H[ih] * U[iu];
          pi[m][x] = q ? fmaf(H[ih], U[iu + 8], pi[m][x]) : H[ih] * U[iu + 8];
          pr[m][x] = fmaf(-H[ih + 8], U[iu + 8], pr[m][x]);
          pi[m][x] = fmaf(H[ih + 8], U[iu], pi[m][x]);
        }
      }
    }
#pragma unroll
    for (int m = 0; m < 4; m++) {
      a[m & 2][2 * j + (m & 1)] = pack2(pr[m][0], pr[m][1]);
      a[(m & 2) + 1][2 * j + (m & 1)] = pack2(pi[m][0], pi[m][1]);
    }
  }
  wg_fence();
  g_step(U, a, dg + 64, dg);
  const uint32_t za = cb + U_BYTES + (8 * w + (lane & 7)) * 128 + (((lane >> 3) ^ (lane & 7)) << 4);
  const uint32_t ya = cb + (lane >> 4) * 1024 + (8 * w + (lane & 7)) * 32 + ((((lane >> 3) ^ (lane >> 2)) & 1) << 4);
  wg_sync(1 + wg);
  wg_wait<0>();
  pin<32>(U);
  TSIF(w == 0, 80 + c);
#pragma unroll
  for (int p = 0; p < 2; p++) {
#pragma unroll
    for (int i = 0; i < 4; i++) {
      const int j = i & 1;
      float* x = U + 16 * p + 4 * j + (i & 2);
      rot<true>(x[8], x[0], k.ta[2 * j], k.tb[2 * j]);
      rot<true>(x[9], x[1], k.ta[2 * j + 1], k.tb[2 * j + 1]);
      e[p][i] = pack2(x[8], x[9]);
      e[2 + p][i] = pack2(x[0], x[1]);
    }
    stsm4(za ^ (64 * p), e[p]);
    stsm4((za ^ (64 * p)) + 4096, e[2 + p]);
  }
  fence_async_smem();
  wg_sync(1 + wg);
  wg_fence();
  WgRS<64>::set<HI_SW128>(H, k.fi[0], dz);
#pragma unroll
  for (int ks = 1; ks < 4; ks++) WgRS<64>::mma<HI_SW128>(H, k.fi[ks], dz + 128 * ks);
  wg_commit();
  wg_wait<0>();
  pin<32>(H);
  TSIF(w == 0, 88 + c);
#pragma unroll
  for (int j = 0; j < 8; j++)
    a[j >> 2][j & 3] = j < 2 ? pack2(H[4 * j], H[4 * j + 1]) : pack2(H[4 * j] + H[4 * j - 6], H[4 * j + 1] + H[4 * j - 5]);
  stsm4(ya, a[0]);
  stsm4(ya + 2048, a[1]);
  fence_async_smem();
  __syncwarp();
}

__device__ __forceinline__ void prep_slab(uint4* res, const uint2* sw, uint32_t sb, int slab, int w, int lane) {
  const int t = lane & 3, tp = (lane & 7) >> 1, pos = 8 * tp + 2 * (((lane >> 3) + tp) & 3) + (lane & 1);
  const uint32_t base = sb + OFF_KVS + slab * KVS_BYTES + pos * 128;
  uint32_t kk[2][4][4], vv[2][4];
  mbar_wait(sb + OFF_BAR + 8 * (B_KV + slab), 0);
#pragma unroll
  for (int h = 0; h < 2; h++) {
#pragma unroll
    for (int j = 0; j < 4; j++) {
      const uint32_t a = base + 128 * j;
      ldsm4t(kk[h][j], a + (((w + 4 * h) ^ ((a >> 7) & 7)) << 4));
    }
    const uint32_t a = base + KVS_V;
    ldsm4t(vv[h], a + (((w + 4 * h) ^ ((a >> 7) & 7)) << 4));
  }
#pragma unroll
  for (int h = 0; h < 2; h++) {
    uint32_t (&k)[4][4] = kk[h];
    uint32_t (&v)[4] = vv[h];
    const uint32_t w0 = __byte_perm(sw[h].x, 0, 0x1010), w1 = __byte_perm(sw[h].x, 0, 0x3232);
    const uint32_t w2 = __byte_perm(sw[h].y, 0, 0x1010), w3 = __byte_perm(sw[h].y, 0, 0x3232);
#pragma unroll
    for (int m = 0; m < 4; m++)
      v[m] = bmul(badd(badd(badd(bmul(k[0][m], w3), bmul(k[1][m], w2)), bmul(k[2][m], w1)), bmul(k[3][m], w0)), v[m]);
    uint32_t a[4];
#pragma unroll
    for (int m = 0; m < 4; m++) a[m] = (t & 1) ? v[(m + 3) & 3] : v[m];
    res[h] = (t & 2) ? make_uint4(a[2], a[3], a[0], a[1]) : make_uint4(a[0], a[1], a[2], a[3]);
  }
}

__device__ __forceinline__ void prep_gate(const Params& p, int b, int w, int lane) {
  uint2 gw[5], x[4][5];
#pragma unroll
  for (int j = 0; j < 5; j++) gw[j] = ldg64(reinterpret_cast<const uint2*>(p.gate_w) + lane + 32 * j);
#pragma unroll
  for (int i = 0; i < 4; i++)
#pragma unroll
    for (int j = 0; j < 5; j++)
      x[i][j] = ldg64(reinterpret_cast<const uint2*>(p.q) + (16 * b + 4 * w + i) * (DIM / 4) + lane + 32 * j);
  float s[4];
#pragma unroll
  for (int i = 0; i < 4; i++) {
    s[i] = 0.f;
#pragma unroll
    for (int j = 0; j < 5; j++) {
      const uint32_t m0 = bmul(x[i][j].x, gw[j].x), m1 = bmul(x[i][j].y, gw[j].y);
      s[i] += (bf_lo(m0) + bf_hi(m0)) + (bf_lo(m1) + bf_hi(m1));
    }
  }
  const bool h = lane & 16, q = lane & 8;
  const float a = (h ? s[2] : s[0]) + __shfl_xor_sync(0xffffffffu, h ? s[0] : s[2], 16);
  const float c = (h ? s[3] : s[1]) + __shfl_xor_sync(0xffffffffu, h ? s[1] : s[3], 16);
  float z = (q ? c : a) + __shfl_xor_sync(0xffffffffu, q ? a : c, 8);
#pragma unroll
  for (int o = 4; o > 0; o >>= 1) z += __shfl_xor_sync(0xffffffffu, z, o);
  z = bf_lo(pack2(z, 0.f));
  if ((lane & 7) == 0) g_gate[16 * b + 4 * w + (lane >> 3)] = bf_lo(pack2(__fdividef(1.f, 1.f + __expf(-z)), 0.f));
}

__device__ __forceinline__ uint32_t bmax(uint32_t a, uint32_t b) {
  uint32_t d;
  asm("max.bf16x2 %0, %1, %2;" : "=r"(d) : "r"(a), "r"(b));
  return d;
}
__device__ __forceinline__ void softmax_two(const float (&l)[2][2], uint32_t& p0, uint32_t& p1) {
  constexpr float kScale = 0.22360679774997896f, kLog2e = 1.4426950408889634f;
  const uint32_t r0 = pack2(l[0][0], l[1][0]), r1 = pack2(l[0][1], l[1][1]);
  const uint32_t x0 = pack2(bf_lo(r0) * kScale, bf_hi(r0) * kScale), x1 = pack2(bf_lo(r1) * kScale, bf_hi(r1) * kScale);
  uint32_t m = bmax(x0, x1);
  m = bmax(m, __shfl_xor_sync(0xffffffffu, m, 1));
  m = bmax(m, __shfl_xor_sync(0xffffffffu, m, 2));
  const float m0 = bf_lo(m) * kLog2e, m1 = bf_hi(m) * kLog2e;
  p0 = pack2(ex2(bf_lo(x0) * kLog2e - m0), ex2(bf_lo(x1) * kLog2e - m0));
  p1 = pack2(ex2(bf_hi(x0) * kLog2e - m1), ex2(bf_hi(x1) * kLog2e - m1));
}

__device__ __forceinline__ void halo_read(uint32_t (&kpv)[10], uint32_t (&vpv)[10], uint32_t (&tg)[7], const uint4* hp) {
#pragma unroll
  for (int j = 0; j < 7; j++) {
    uint32_t x0, x1, x2;
    asm volatile("ld.relaxed.gpu.global.v4.u32 {%0, %1, %2, %3}, [%4];"
                 : "=r"(x0), "=r"(x1), "=r"(x2), "=r"(tg[j]) : "l"(hp + 32 * j) : "memory");
    if (j < 4) kpv[3 * j] = x0; else vpv[3 * j - 10] = x0;
    if (j < 3) kpv[3 * j + 1] = x1; else vpv[3 * j - 9] = x1;
    if (j < 3) kpv[3 * j + 2] = x2; else if (j < 6) vpv[3 * j - 8] = x2;
  }
}

template <int ROT>
__device__ __forceinline__ void pack_qkv(const float* acc, uint32_t (&qlo)[10], uint32_t (&qhi)[10], uint32_t (&klo)[10],
                                         uint32_t (&khi)[10], uint32_t (&vlo)[10], uint32_t (&vhi)[10]) {
#pragma unroll
  for (int j = 0; j < 10; j++) {
    const int x = (j + ROT) % 10, tq = x < 8 ? x : 16 + x, tk = x < 8 ? 8 + x : 18 + x, tv = x < 8 ? 16 + x : 20 + x;
    khi[j] = pack2(acc[4 * tk + 2], acc[4 * tk + 3]);
    vhi[j] = movm(pack2(acc[4 * tv + 2], acc[4 * tv + 3]));
    qlo[j] = pack2(acc[4 * tq], acc[4 * tq + 1]);
    qhi[j] = pack2(acc[4 * tq + 2], acc[4 * tq + 3]);
    klo[j] = pack2(acc[4 * tk], acc[4 * tk + 1]);
    vlo[j] = pack2(acc[4 * tv], acc[4 * tv + 1]);
    asm volatile("" : "+r"(khi[j]), "+r"(qlo[j]), "+r"(qhi[j]), "+r"(klo[j]), "+r"(vlo[j]));
  }
}

template <int ROT> __device__ __forceinline__ void halo_send(const float* acc, uint4* ho, uint32_t tag) {
#pragma unroll
  for (int j = 0; j < 7; j++) {
    uint32_t x[3];
#pragma unroll
    for (int e = 0; e < 3; e++) {
      const int i = 3 * j + e, y = (i % 10 + ROT) % 10, tk = y < 8 ? 8 + y : 18 + y, tv = y < 8 ? 16 + y : 20 + y;
      x[e] = i < 10 ? pack2(acc[4 * tk + 2], acc[4 * tk + 3]) : i < 20 ? movm(pack2(acc[4 * tv + 2], acc[4 * tv + 3])) : 0u;
    }
    asm volatile("st.relaxed.gpu.global.v4.u32 [%0], {%1, %2, %3, %4};" ::"l"(ho + 32 * j), "r"(x[0]), "r"(x[1]), "r"(x[2]), "r"(tag) : "memory");
  }
}

__device__ __forceinline__ void attention(float* acc, uint32_t sb, int b, int par, int w, int lane, uint32_t tag) {
  const int g = lane >> 2, t = lane & 3;
  uint32_t klo[10], khi[10], vlo[10], vhi[10], qlo[10], qhi[10], kpv[10], vpv[10];
  if (HALO_FIRST && w == 3 && b < NCTA - 8) {
    uint4* ho = g_halo + (b * 2 + par) * 224 + lane;
    if (tail_first(b & 7)) halo_send<8>(acc, ho, tag);
    else halo_send<0>(acc, ho, tag);
    TSIF(par == 0, 76);
    pin<120>(acc);
  }
  if (tail_first(b & 7)) pack_qkv<8>(acc, qlo, qhi, klo, khi, vlo, vhi);
  else pack_qkv<0>(acc, qlo, qhi, klo, khi, vlo, vhi);
  const uint32_t xa = sb + OFF_KVX + (par * 3) * 2560 + lane * 16;
  if (w < 3) {
    sts128(xa + w * 2560, khi[0], khi[1], khi[2], khi[3]);
    sts128(xa + w * 2560 + 512, khi[4], khi[5], khi[6], khi[7]);
    sts128(xa + w * 2560 + 1024, khi[8], khi[9], vhi[0], vhi[1]);
    sts128(xa + w * 2560 + 1536, vhi[2], vhi[3], vhi[4], vhi[5]);
    sts128(xa + w * 2560 + 2048, vhi[6], vhi[7], vhi[8], vhi[9]);
  } else if (!HALO_FIRST && b < NCTA - 8) {
    uint4* ho = g_halo + (b * 2 + par) * 224 + lane;
#pragma unroll
    for (int j = 0; j < 7; j++) {
      const uint32_t x0 = j < 4 ? khi[3 * j] : vhi[3 * j - 10], x1 = j < 3 ? khi[3 * j + 1] : vhi[3 * j - 9];
      const uint32_t x2 = j < 3 ? khi[3 * j + 2] : j < 6 ? vhi[3 * j - 8] : 0u;
      asm volatile("st.relaxed.gpu.global.v4.u32 [%0], {%1, %2, %3, %4};" ::"l"(ho + 32 * j), "r"(x0), "r"(x1), "r"(x2), "r"(tag) : "memory");
    }
  }
  TSIF(par == 0 && w == 1, 64);
  TSIF(par == 0 && w == 3 && !HALO_FIRST, 76);
#pragma unroll
  for (int j = 0; j < 10; j++) vlo[j] = movm(vlo[j]);
  const bool far0 = 2 * t > g, far1 = 2 * t + 1 > g;
  const uint32_t mfar = (far0 ? 0x0000FFFFu : 0u) | (far1 ? 0xFFFF0000u : 0u);
  float slo[4][2], shi[4][2], lg[2][2];
  uint32_t phi[4], plo[4], qml[4], qmh[4];
#pragma unroll
  for (int h = 0; h < 4; h++) {
    const int f = h == 0 ? 0 : h == 1 ? 3 : h == 2 ? 5 : 8, hf = h < 2 ? 2 : 7;
    const bool mine = (h & 1) ? t >= 2 : t < 2;
    qml[h] = mine ? qlo[hf] : 0u;
    qmh[h] = mine ? qhi[hf] : 0u;
    float a[4] = {0.f, 0.f, 0.f, 0.f}, c[4] = {0.f, 0.f, 0.f, 0.f};
    mma16816(a, qlo[f], qhi[f], qlo[f + 1], qhi[f + 1], klo[f], klo[f + 1]);
    mma16816(c, qlo[f], qhi[f], qlo[f + 1], qhi[f + 1], khi[f], khi[f + 1]);
    mma1688(a, qml[h], qmh[h], klo[hf]);
    mma1688(c, qml[h], qmh[h], khi[hf]);
    slo[h][0] = a[0];
    slo[h][1] = a[1];
    shi[h][0] = lg[h & 1][0] = far0 ? a[2] : c[2];
    shi[h][1] = lg[h & 1][1] = far1 ? a[3] : c[3];
    if (!ATT_MERGE && (h & 1)) softmax_two(lg, phi[h - 1], phi[h]);
  }
  TSIF(par == 0 && w == 1, 65);
  wg_sync(1 + par);
  TSIF(par == 0 && w == 1, 66);
  const bool nohist = (w == 0) && (b < 8);
  const uint4* hp = g_halo + ((b - 8) * 2 + par) * 224 + lane;
  uint32_t tg[7];
  if (w > 0) {
    const uint4 v0 = lds128(xa + (w - 1) * 2560), v1 = lds128(xa + (w - 1) * 2560 + 512), v2 = lds128(xa + (w - 1) * 2560 + 1024);
    const uint4 v3 = lds128(xa + (w - 1) * 2560 + 1536), v4 = lds128(xa + (w - 1) * 2560 + 2048);
    kpv[0] = v0.x; kpv[1] = v0.y; kpv[2] = v0.z; kpv[3] = v0.w; kpv[4] = v1.x; kpv[5] = v1.y; kpv[6] = v1.z; kpv[7] = v1.w;
    kpv[8] = v2.x; kpv[9] = v2.y; vpv[0] = v2.z; vpv[1] = v2.w; vpv[2] = v3.x; vpv[3] = v3.y; vpv[4] = v3.z; vpv[5] = v3.w;
    vpv[6] = v4.x; vpv[7] = v4.y; vpv[8] = v4.z; vpv[9] = v4.w;
  } else if (nohist) {
#pragma unroll
    for (int j = 0; j < 10; j++) kpv[j] = vpv[j] = 0u;
  } else {
    TSIF(par == 0, 77);
    halo_read(kpv, vpv, tg, hp);
  }
  if (w == 0 && !nohist) {
    int spins = 0;
    while (true) {
      bool ok = true;
#pragma unroll
      for (int j = 0; j < 7; j++) ok = ok && tg[j] == tag;
      if (__all_sync(0xffffffffu, ok) || ++spins > SPIN_LIMIT) break;
      halo_read(kpv, vpv, tg, hp);
    }
    TSIF(par == 0, 79);
  }
#pragma unroll
  for (int h = 0; h < 4; h++) {
    const int f = h == 0 ? 0 : h == 1 ? 3 : h == 2 ? 5 : 8, hf = h < 2 ? 2 : 7;
    float a[4] = {0.f, 0.f, 0.f, 0.f};
    mma16816(a, qlo[f], qhi[f], qlo[f + 1], qhi[f + 1], kpv[f], kpv[f + 1]);
    mma1688(a, qml[h], qmh[h], kpv[hf]);
    const float ninf = __int_as_float(0xff800000);
    lg[h & 1][0] = far0 ? (nohist ? ninf : a[0]) : slo[h][0];
    lg[h & 1][1] = far1 ? (nohist ? ninf : a[1]) : slo[h][1];
    if (h & 1) {
      softmax_two(lg, plo[h - 1], plo[h]);
      if (ATT_MERGE) {
        const float lh[2][2] = {{shi[h - 1][0], shi[h - 1][1]}, {shi[h][0], shi[h][1]}};
        softmax_two(lh, phi[h - 1], phi[h]);
      }
    }
  }
  TSIF(par == 0 && w <= 1, 67 + w);
  uint32_t ov[20];
#pragma unroll
  for (int hp = 0; hp < 2; hp++) {
    const int hf = hp ? 7 : 2;
    float sh[4] = {0.f, 0.f, 0.f, 0.f}, i0 = 0.f, i1 = 0.f;
#pragma unroll
    for (int e = 0; e < 2; e++) {
      const int h = 2 * hp + e, f = h == 0 ? 0 : h == 1 ? 3 : h == 2 ? 5 : 8;
      const uint32_t a0 = plo[h] & mfar, a2 = plo[h] & ~mfar, a3 = phi[h] & mfar, c1 = phi[h] & ~mfar;
      float sum[4] = {0.f, 0.f, 0.f, 0.f};
      mma1688(sum, plo[h], phi[h], 0x3F803F80u);
      const float r0 = rcp(sum[0]), r1 = rcp(sum[2]);
#pragma unroll
      for (int j = f; j < f + 2; j++) {
        float o[4] = {0.f, 0.f, 0.f, 0.f};
        mma16816(o, a0, 0u, a2, a3, vpv[j], vlo[j]);
        mma1688(o, 0u, c1, vhi[j]);
        ov[2 * j] = pack2(o[0] * r0, o[1] * r0);
        ov[2 * j + 1] = pack2(o[2] * r1, o[3] * r1);
      }
      const bool mine = e ? g >= 4 : g < 4;
      mma16816(sh, a0, 0u, a2, a3, mine ? vpv[hf] : 0u, mine ? vlo[hf] : 0u);
      mma1688(sh, 0u, c1, mine ? vhi[hf] : 0u);
      if (e == 0 || t >= 2) {
        i0 = r0;
        i1 = r1;
      }
    }
    ov[2 * hf] = pack2(sh[0] * i0, sh[1] * i0);
    ov[2 * hf + 1] = pack2(sh[2] * i1, sh[3] * i1);
  }
  TS(32 + 4 * par + w);
  mbar_wait(sb + OFF_BAR + 8 * B_P1, 0);
  const uint32_t oa = sb + OFF_OA + (lane >> 4) * 2048 + (32 * w + 2 * (lane & 15) + par) * 16;
#pragma unroll
  for (int j = 0; j < 5; j++) stsm4(oa + 4096 * j, ov + 4 * j);
  TSIF(par == 0 && w == 0, 120);
  fence_async_smem();
  TSIF(par == 0 && w == 0, 121);
  __syncwarp();
  if (lane == 0) mbar_arrive(sb + OFF_BAR + 8 * B_ATTN);
  TSIF(par == 0 && w == 0, 122);
}

struct Maps {
  CUtensorMap x, wm, wt, k, v, y, wo, qm, qt, om, ot, u;
};

__device__ __forceinline__ void load_stage(uint32_t sb, int kb, int b, const Maps& m) {
  const uint32_t st = sb + (kb & 3) * STAGE_BYTES, bar = sb + OFF_BAR + 8 * (B_FULL1 + (kb & 3));
  const int r = b >> 3, hg = b & 7, slab = kb - KV_KB;
  const bool kv = slab >= 0 && slab < 5;
  const uint32_t kbar = sb + OFF_BAR + 8 * (B_KV + slab), dst = sb + OFF_KVS + slab * KVS_BYTES;
  mbar_expect_tx(bar, STAGE_BYTES);
  if (kv) mbar_expect_tx(kbar, KVS_BYTES);
  tma_3d(st, &m.x, 64 * kb, 64 * r, 0, bar);
  if (kv && KV_MIX) tma_3d(dst, &m.k, 0, 32 * (b >> 1) - 3, 2 * slab + (b & 1), kbar);
  tma_3d(st + ST_W, &m.wm, 80 * hg + (tail_first(hg) ? 16 : 0), 64 * kb, 0, bar);
  if (kv && KV_MIX) tma_3d(dst + KVS_V, &m.v, 0, 32 * (b >> 1), 2 * slab + (b & 1), kbar);
  tma_3d(st + ST_WT, &m.wt, 80 * hg + (tail_first(hg) ? 0 : 64), 64 * kb, 0, bar);
  if (kv && !KV_MIX) tma_3d(dst, &m.k, 0, 32 * (b >> 1) - 3, 2 * slab + (b & 1), kbar);
  if (kv && !KV_MIX) tma_3d(dst + KVS_V, &m.v, 0, 32 * (b >> 1), 2 * slab + (b & 1), kbar);
}

__global__ void __launch_bounds__(NTHR, 1) fused_kernel(const __grid_constant__ Maps m, const Params p) {
  extern __shared__ __align__(1024) uint8_t smem[];
  const uint32_t sb = (uint32_t)__cvta_generic_to_shared(smem);
  const uint32_t bars = sb + OFF_BAR;
  const int tid = threadIdx.x, lane = tid & 31;
  int b = blockIdx.x;
  if (BMAP == 1) b = (((b & 63) >> 3) * 2 + (b & 1)) * 8 + (((b < 64 ? 0x6521 : 0x7430) >> (4 * ((b >> 1) & 3))) & 7);
  if (BMAP == 2) b = ((b & 63) >> 2) * 8 + (((b < 64 ? 0x6521 : 0x7430) >> (4 * (b & 3))) & 7);
  if (BMAP == 3) b = (((b & 63) >> 3) * 2 + (b & 1)) * 8 + (((b < 64 ? 0x7430 : 0x6521) >> (4 * ((b >> 1) & 3))) & 7);
  if (BMAP == 4) b = (((b >> 4) * 2 + (b & 1)) * 8) + ((b >> 1) & 7);
  if (BMAP == 5) b = 127 - b;
  const int r = b >> 3, hg = b & 7;

  if (tid < 32 * PF_KB) {
    const int i = blockIdx.x * 32 + lane, kb = tid >> 5, j = i - 2048;
    const char* a = i < 2048 ? reinterpret_cast<const char*>(p.q) + i * 1280 + kb * 128
                             : reinterpret_cast<const char*>(p.wqkv) + (64 * kb + j / 30) * 3840 + (j % 30) * 128;
    if (j < 1920) asm volatile("prefetch.global.L2 [%0];" ::"l"(a) : "memory");
  }
  if (tid == T_ISSUE) {
    TSM(true, 0);
#pragma unroll
    for (int i = 0; i < 4; i++) mbar_init(bars + 8 * (B_FULL1 + i), 1);
#pragma unroll
    for (int i = 0; i < 3; i++) mbar_init(bars + 8 * (B_KV + i), 1);
    fence_async_smem();
#pragma unroll 1
    for (int kb = 0; kb <= PRE2; kb++) load_stage(sb, kb, b, m);
  } else if (tid >= T_PF && tid < T_PF + 12) {
    tm_prefetch(&m.x + (tid - T_PF));
  } else if (tid == T_INIT) {
#pragma unroll
    for (int i = 0; i < 4; i++) mbar_init(bars + 8 * (B_EMPTY1 + i), 8);
#pragma unroll
    for (int i = 0; i < 8; i++) mbar_init(bars + 8 * (B_FULL2 + i), 1);
#pragma unroll
    for (int i = 0; i < 4; i++) mbar_init(bars + 8 * (B_EMPTY2 + i), 8);
#pragma unroll
    for (int i = 0; i < 4; i++) mbar_init(bars + 8 * (B_U + i), 1);
    mbar_init(bars + 8 * B_HA, 4);
    mbar_init(bars + 8 * B_GATE, 4);
    mbar_init(bars + 8 * B_HB, 1);
    mbar_init(bars + 8 * B_KVD, 4);
    mbar_init(bars + 8 * B_QF, 1);
    mbar_init(bars + 8 * B_ATTN, 8);
    mbar_init(bars + 8 * B_P1, 8);
    mbar_init(bars + 8 * B_C34, 1);
#pragma unroll
    for (int i = 0; i < 5; i++) mbar_init(bars + 8 * (B_YST + i), 4);
#pragma unroll
    for (int i = 0; i < 5; i++) mbar_init(bars + 8 * (B_US + i), 4);
    mbar_init(bars + 8 * B_YSIG, 1);
    mbar_init(bars + 8 * B_YFULL, 1);
    mbar_init(bars + 8 * B_EPOCH, 1);
    mbar_init(bars + 8 * B_PREP, 4);
    mbar_init(bars + 8 * B_USIG, 1);
    mbar_init(bars + 8 * B_WST, 1);
#pragma unroll
    for (int i = 3; i < 5; i++) mbar_init(bars + 8 * (B_KV + i), 1);
    mbar_init(bars + 8 * B_E3, 8);
    mbar_init(bars + 8 * B_LAST, 1);
    mbar_init(bars + 8 * B_OSIG, 1);
    mbar_init(bars + 8 * B_WOP, 1);
    fence_async_smem();
  }
  const int warp = __shfl_sync(0xffffffffu, tid >> 5, 0), wg = warp >> 2, w = warp & 3;
  __syncthreads();

  if (wg == 3) {
    asm volatile("setmaxnreg.dec.sync.aligned.u32 56;");
    if (w == 0) {
      if (lane == 0) {
#pragma unroll 1
        for (int kb = 1 + PRE2; kb < 10; kb++) {
          if (kb >= 4) mbar_wait(bars + 8 * (kb == 7 ? B_E3 : B_EMPTY1 + (kb & 3)), (kb >> 3) & 1);
          TSIF(kb >= 4, 44 + kb);
          load_stage(sb, kb, b, m);
          TSIF(kb == 3, 60);
          if (kb == TRIG_KB) mbar_arrive(bars + 8 * B_LAST);
        }
        mbar_wait(bars + 8 * B_WOP, 0);
        mbar_wait(bars + 8 * WL_TRIG, 0);
        mbar_wait(bars + 8 * B_EPOCH, 0);
        flag_wait(g_cnt + C_W + 32 * hg, (lds32(sb + OFF_EPOCH) + 1) * 16);
        TS(30);
#pragma unroll 1
        for (int j = 0; j < 8; j++) {
          if (j >= 6) mbar_wait(bars + 8 * (B_EMPTY2 + j - 6), 0);
          if (j == 4) mbar_wait(bars + 8 * B_ATTN, 0);
          TSIF(j >= 6, 100 + j);
          if (RF_GATE && j == 6) mbar_wait(bars + 8 * B_YSIG, 0);
          mbar_expect_tx(bars + 8 * (B_FULL2 + j), j == 0 ? WO_BYTES : j == 5 ? O_BYTES + WO_BYTES + 512 : O_BYTES + WO_BYTES);
          bulk_load(sb + off_w(j), g_WO + (hg * 8 + step_src(hg, j)) * 800, WO_BYTES, bars + 8 * (B_FULL2 + j));
        }
        mbar_wait(bars + 8 * (B_EMPTY2 + 3), 0);
        mbar_expect_tx(bars + 8 * B_QF, O_BYTES);
        tma_2d(sb + OFF_QS, &m.qm, 80 * hg, 128 * r, bars + 8 * B_QF);
        tma_2d(sb + OFF_QT, &m.qt, 80 * hg + 64, 128 * r, bars + 8 * B_QF);
      }
    } else if (w == 1) {
      unsigned epoch = 0;
      if (lane == 0) {
        epoch = atomicAdd(g_cnt + C_LAUNCH, 1u) / NCTA;
        asm volatile("st.shared.u32 [%0], %1;" ::"r"(sb + OFF_EPOCH), "r"(epoch) : "memory");
        mbar_arrive(bars + 8 * B_EPOCH);
        mbar_wait(bars + 8 * B_KVD, 0);
        mbar_expect_tx(bars + 8 * B_HB, 5 * 4096);
#pragma unroll 1
        for (int c = 0; c < 5; c++) {
          if (c == 3) mbar_wait(bars + 8 * B_S3, 0);
          bulk_load(sb + off_ch(c) + U_BYTES, p.ssm_k + (5 * b + c) * SEQ, 4096, bars + 8 * B_HB);
        }
#pragma unroll
        for (int c = 0; c < 4; c++) mbar_expect_tx(bars + 8 * (B_U + c), c < 3 ? U_BYTES : 2 * U_BYTES);
        const uint4* usrc = g_U + 5 * b * U_PITCH;
        mbar_wait(bars + 8 * B_USIG, 0);
        flag_wait(g_cnt + C_PREP + 32 * (b & 15), (epoch + 1) * NCTA);
        TS(23);
#pragma unroll
        for (int c = 0; c < 5; c++) {
          if (c == 3) mbar_wait(bars + 8 * (B_U + 2), 0);
          bulk_load(sb + off_ch(c), usrc + c * U_PITCH, U_BYTES, bars + 8 * (B_U + (c < 3 ? c : 3)));
          TSIF(c == 0 || c == 4, 116 + (c >> 2));
        }
      }
      epoch = __shfl_sync(0xffffffffu, epoch, 0);
      if (lane < 8) {
        const int src = (b & ~7) | step_src(hg, lane);
        mbar_wait(bars + 8 * B_OSIG, 0);
        TS(20);
        flag_wait(g_cnt + C_O + 32 * src, epoch + 1);
        if (lane >= 1 && lane < 4) bulk_load(sb + off_o(lane), g_O + src * 1280, O_BYTES, bars + 8 * (B_FULL2 + lane));
        __syncwarp(0xff);
        TS(21);
        if (lane == 5) bulk_load(sb + OFF_GATE, g_gate + 128 * r, 512, bars + 8 * (B_FULL2 + 5));
#pragma unroll 1
        for (int j = 4; j < 8; j++) {
          if (lane == j) {
            mbar_wait(bars + 8 * (j < 6 ? B_C34 : B_EMPTY2 + j - 6), 0);
            if (RF_GATE && j == 6) mbar_wait(bars + 8 * B_YSIG, 0);
            bulk_load(sb + off_o(j), g_O + src * 1280, O_BYTES, bars + 8 * (B_FULL2 + j));
          }
          __syncwarp(0xff);
        }
        TS(22);
      }
    } else if (w == 2) {
      mbar_wait(bars + 8 * B_PREP, 0);
      flag_signal(g_cnt + C_PREP, 16, lane);
      TS(25);
      if (lane == 0) mbar_arrive(bars + 8 * B_USIG);
      mbar_wait(bars + 8 * B_GATE, 0);
      if ((NOMB & 1) && lane == 0) asm volatile("fence.release.gpu;" ::: "memory");
      mbar_wait(bars + 8 * B_ATTN, 0);
      if (lane == 0) {
        if (O_DEFER) mbar_wait(bars + 8 * (B_U + 3), 0);
        asm volatile("cp.async.bulk.global.shared::cta.bulk_group [%0], [%1], 20480;\ncp.async.bulk.commit_group;\n"
                     "cp.async.bulk.wait_group 0;\nfence.proxy.async.global;" ::"l"(g_O + b * 1280), "r"(sb + OFF_OA) : "memory");
      }
      TS(74);
      if (!(NOMB & 1)) flag_signal(g_cnt + C_O + 32 * b, 1, lane);
      else if (lane == 0) flag_bump(g_cnt + C_O + 32 * b);
      TS(26);
      if (lane == 0) mbar_arrive(bars + 8 * B_OSIG);

    } else {
      if (lane == 0) {
        uint4* dst = g_WO + (hg * 8 + (r >> 1)) * 800 + (r & 1) * 80;
        mbar_wait(bars + 8 * B_P1, 0);
        mbar_wait(bars + 8 * WB_TRIG, 0);
        mbar_expect_tx(bars + 8 * B_WST, WO_BYTES / 2);
        tma_3d(sb + OFF_WS, &m.wo, 0, 40 * r, 5 * hg, bars + 8 * B_WST);
        mbar_wait(bars + 8 * B_WST, 0);
        mbar_wait(bars + 8 * WO_TRIG, 0);
#pragma unroll 1
        for (int n = 0; n < 5; n++)
          asm volatile("cp.async.bulk.global.shared::cta.bulk_group [%0], [%1], 1280;" ::"l"(dst + 160 * n), "r"(sb + OFF_WS + 1280 * n) : "memory");
        asm volatile("cp.async.bulk.commit_group;\ncp.async.bulk.wait_group 0;\nfence.proxy.async.global;" ::: "memory");
        if (!(NOMB & 4)) asm volatile("fence.release.gpu;" ::: "memory");
        flag_bump(g_cnt + C_W + 32 * hg);
        mbar_arrive(bars + 8 * B_WOP);
        TS(71);
#pragma unroll 1
        for (int c = 0; c < 5; c++) {
          mbar_wait(bars + 8 * (B_YST + c), 0);
          asm volatile("cp.async.bulk.global.shared::cta.bulk_group [%0], [%1], 4096;\ncp.async.bulk.commit_group;"
                       ::"l"(g_Y + (5 * b + c) * Y_PITCH), "r"(sb + off_ch(c)) : "memory");
          if (c == 2) {
            asm volatile("cp.async.bulk.wait_group.read 0;" ::: "memory");
            mbar_arrive(bars + 8 * B_C34);
          }
        }
        asm volatile("cp.async.bulk.wait_group 0;\nfence.proxy.async.global;" ::: "memory");
        TS(75);
        if (!(NOMB & 2)) asm volatile("fence.release.gpu;" ::: "memory");
        flag_bump(g_cnt + C_Y + 32 * (b >> 4));
        TS(27);
        mbar_arrive(bars + 8 * B_YSIG);
        mbar_expect_tx(bars + 8 * B_YFULL, 20480);
        flag_wait(g_cnt + C_Y + 32 * hg, (lds32(sb + OFF_EPOCH) + 1) * 16);
        TS(24);
        tma_2d(sb + OFF_YT, &m.y, 128 * r, 80 * hg, bars + 8 * B_YFULL);
        tma_2d(sb + OFF_YT + 10240, &m.y, 128 * r + 64, 80 * hg, bars + 8 * B_YFULL);
      }
    }
  } else {
    asm volatile("setmaxnreg.inc.sync.aligned.u32 152;");
    if (wg < 2) {
      float acc[120];
#pragma unroll
      for (int i = 0; i < 120; i++) acc[i] = 0.f;
      const uint32_t da = desc_lo(sb + wg * 8192, 16), db = desc_lo(sb + ST_W, 8192), dc = desc_lo(sb + ST_WT, 2048);
      if (PW1) pin<120>(acc);
      if (PW1 == 2) mbar_wait(bars + 8 * B_FULL1, 0);
#pragma unroll 1
      for (int kb = 0; kb < 10; kb++) {
        mbar_wait(bars + 8 * (B_FULL1 + (kb & 3)), (kb >> 2) & 1);
        const uint32_t so = (kb & 3) * (STAGE_BYTES >> 4);
        wg_fence();
#pragma unroll
        for (int k = 0; k < 4; k++) {
          WgSST<192>::mma<HI_SW128, HI_SW128>(acc, da + so + 2 * k, db + so + 128 * k, 1);
          WgSST<48>::mma<HI_SW128, HI_SW32>(acc + 96, da + so + 2 * k, dc + so + 32 * k, 1);
        }
        wg_commit();
        wg_wait<1>();
        if (kb > 0 && lane == 0) mbar_arrive(bars + 8 * (kb == 4 ? B_E3 : B_EMPTY1 + ((kb - 1) & 3)));
      }
      mbar_wait(bars + 8 * B_EPOCH, 0);
      const uint32_t tag = lds32(sb + OFF_EPOCH) + 1;
      mbar_wait(bars + 8 * B_S3, 0);
      wg_wait<0>();
      pin<120>(acc);
      if (lane == 0) mbar_arrive(bars + 8 * B_P1);
      TSM(w == 0, 3 + wg);
      attention(acc, sb, b, wg, w, lane, tag);
    } else {
      const int tw = tid & 127, chl = 64 * (b & 1) + 8 * w + (lane >> 2);
      uint4* up = g_U + chl * U_PITCH + ((4 * (b >> 1) + (lane & 3)) ^ ((b >> 2) & 1));
      uint2 sw[10];
      uint32_t dv = 0;
      if (lane < 5) dv = __ldg(reinterpret_cast<const unsigned short*>(p.ssm_D) + 5 * b + lane);
#pragma unroll
      for (int i = 0; i < 10; i++) sw[i] = ldg64(reinterpret_cast<const uint2*>(p.shift_k) + chl + 128 * (i >> 1) + 32 * (i & 1));
      uint32_t tab[12];
      fft_tables(tab, tw);
      uint4 res[10];
#pragma unroll
      for (int i = 0; i < 10; i++) res[i] = make_uint4(0, 0, 0, 0);
#pragma unroll 1
      for (int slab = 0; slab < 5; slab++) {
#pragma unroll
        for (int i = 0; i < 8; i++) res[i] = res[i + 2];
        prep_slab(res + 8, sw, sb, slab, w, lane);
        TSIF(w == 0, 99 + 4 * slab);
#pragma unroll
        for (int i = 0; i < 8; i++) sw[i] = sw[i + 2];
      }
      TSIF(w == 0, 28);
      __syncwarp();
      if (lane == 0) mbar_arrive(bars + 8 * B_KVD + ((res[8].x ^ res[9].x) & p.zero));
      mbar_wait(bars + 8 * B_KVD, 0);
      fft_tables_store(tab, sb, tw);
      mbar_wait(bars + 8 * B_LAST, 0);
#pragma unroll
      for (int i = 0; i < 10; i++) up[(128 * (i >> 1) + 32 * (i & 1)) * U_PITCH] = res[i];
      __syncwarp();
      if (lane == 0) mbar_arrive(bars + 8 * B_PREP);
      TSIF(w == 0 && !U_TMA, 5);
      mbar_wait(bars + 8 * (G_AFTER ? B_USIG : B_LAST), 0);
      prep_gate(p, b, w, lane);
      __syncwarp();
      if (lane == 0) mbar_arrive(bars + 8 * B_GATE);
      TSIF(w == 0, 72);
      mbar_wait(bars + 8 * B_HB, 0);
      TSIF(w == 0, 123);
      const uint32_t ha = sb + U_BYTES + ((tw >> 3) * 16 + 8 + (tw & 7)) * 16;
      uint4 hv[5];
#pragma unroll
      for (int c = 0; c < 5; c++) hv[c] = lds128(ha + off_ch(c));
      __syncwarp();
#pragma unroll
      for (int c = 0; c < 5; c++) sts128((ha ^ 16) + off_ch(c), hv[c].x, hv[c].y, hv[c].z, hv[c].w);
      if (tw < 5) asm volatile("st.shared.f32 [%0], %1;" ::"r"(sb + OFF_D + 4 * tw), "f"(bf_lo(dv) * 0.125f) : "memory");
      fence_async_smem();
      __syncwarp();
      if (lane == 0) mbar_arrive(bars + 8 * B_HA);
      TSIF(w == 0, 6);
    }

    FftConst fc;
    fft_twiddles(fc, w, lane);
    mbar_wait(bars + 8 * B_HA, 0);
    fft_matrices(fc, sb, w, lane);
    if (ATT_GATE && !H_EARLY) mbar_wait(bars + 8 * B_ATTN, 0);
    TSIF(w == 0 && wg == 2, 124);
#pragma unroll 1
    for (int c = wg == 2 ? 0 : wg + 1; c < 5; c += !CH_W2 ? 3 : wg < 2 ? 5 : c ? 1 : 3) {
      conv_channel(fc, sb, c, wg, w, lane);
      if (lane == 0) mbar_arrive(bars + 8 * (B_YST + c));
      TSM(w == 0, 10 + c);
    }

    if (wg < 2) {
      const int g = lane >> 2;
      float acc[40];
#pragma unroll
      for (int i = 0; i < 40; i++) acc[i] = 0.f;
      const uint32_t da = desc_lo(sb + wg * 1024, 2048), db = desc_lo(sb, 2560);
      mbar_wait(bars + 8 * B_ATTN, 0);
      mbar_wait(bars + 8 * (B_YST + 3), 0);
      mbar_wait(bars + 8 * (B_YST + 4), 0);
      if (PW2) mbar_wait(bars + 8 * B_FULL2, 0);
#pragma unroll 1
      for (int j = 0; j < 8; j++) {
        mbar_wait(bars + 8 * (B_FULL2 + j), 0);
        const uint32_t oa = da + (off_o(j) >> 4), ob = db + (off_w(j) >> 4);
        wg_fence();
#pragma unroll
        for (int k = 0; k < 5; k++) WgSST<80>::mma<HI_NONE, HI_SW32>(acc, oa + 256 * k, ob + 32 * k, 1);
        wg_commit();
        wg_wait<1>();
        if (j >= 1 && j <= 4 && lane == 0) mbar_arrive(bars + 8 * (B_EMPTY2 + j - 1));
      }
      TSIF(w == 0 && wg == 0, 113);
      const int tr = 64 * wg + 16 * w + (lane & 15);
      const uint32_t fm = sb + OFF_QS + tr * 128, fx = (lane >> 4) ^ (tr & 7);
      const uint32_t ft = sb + OFF_QT + tr * 32 + (((lane >> 4) ^ (tr >> 2)) & 1) * 16;
      const float g0 = __uint_as_float(lds32(sb + OFF_GATE + (64 * wg + 16 * w + g) * 4));
      const float g1 = __uint_as_float(lds32(sb + OFF_GATE + (64 * wg + 16 * w + 8 + g) * 4));
      const uint32_t ga = pack2(g0, g0), gb = pack2(g1, g1);
      const uint32_t na = pack2(1.f - g0, 1.f - g0), nb = pack2(1.f - g1, 1.f - g1);

      wg_wait<0>();
      pin<40>(acc);
      TSM(w == 0, 17 + wg);
      uint32_t pb[20];
#pragma unroll
      for (int j = 0; j < 10; j++) {
        pb[2 * j] = bmul(na, pack2(acc[4 * j], acc[4 * j + 1]));
        pb[2 * j + 1] = bmul(nb, pack2(acc[4 * j + 2], acc[4 * j + 3]));
        asm volatile("" : "+r"(pb[2 * j]), "+r"(pb[2 * j + 1]));
      }
      const uint32_t ya = sb + OFF_YT + wg * 10240 + ((lane >> 4) * 8 + (lane & 7)) * 128 +
                          (((2 * w + (((lane >> 3) & 1) ^ wg)) ^ (lane & 7)) << 4);
      uint32_t qf[20];
      mbar_wait(bars + 8 * B_QF, 0);
#pragma unroll
      for (int j = 0; j < 5; j++) ldsm4(qf + 4 * j, j < 4 ? fm + ((fx ^ (2 * j)) << 4) : ft);
      mbar_wait(bars + 8 * B_YFULL, 0);
      TSIF(w == 0 && wg == 0, 19);
#pragma unroll
      for (int j = 0; j < 5; j++) {
        uint32_t y[4];
        ldsm4t(y, ya + 2048 * j);
#pragma unroll
        for (int i = 0; i < 4; i++) qf[4 * j + i] = badd(bmul((i & 1) ? gb : ga, bmul(qf[4 * j + i], y[i])), pb[4 * j + i]);
      }
#pragma unroll
      for (int j = 0; j < 5; j++) stsm4(j < 4 ? fm + ((fx ^ (2 * j)) << 4) : ft, qf + 4 * j);
      fence_async_smem();
      __syncwarp();
      if (lane == 0) {
        const int row = 64 * wg + 16 * w;
        asm volatile("cp.async.bulk.tensor.2d.global.shared::cta.bulk_group [%0, {%2, %3}], [%1];"
                     ::"l"(&m.om), "r"(sb + OFF_QS + row * 128), "r"(80 * hg), "r"(128 * r + row) : "memory");
        asm volatile("cp.async.bulk.tensor.2d.global.shared::cta.bulk_group [%0, {%2, %3}], [%1];"
                     ::"l"(&m.ot), "r"(sb + OFF_QT + row * 32), "r"(80 * hg + 64), "r"(128 * r + row) : "memory");
        asm volatile("cp.async.bulk.commit_group;\ncp.async.bulk.wait_group.read 0;" ::: "memory");
      }
      TSM(true, 40 + 4 * wg + w);
      if (ENDBAR) asm volatile("bar.sync 15, 256;" ::: "memory");
    }
  }
}

typedef CUresult (*EncodeFn)(CUtensorMap*, CUtensorMapDataType, cuuint32_t, void*, const cuuint64_t*, const cuuint64_t*,
                             const cuuint32_t*, const cuuint32_t*, CUtensorMapInterleave, CUtensorMapSwizzle,
                             CUtensorMapL2promotion, CUtensorMapFloatOOBfill);

void encode(EncodeFn fn, CUtensorMap* tm, const void* base, int rank, const cuuint64_t* dims, const cuuint64_t* strides,
            const cuuint32_t* box, CUtensorMapSwizzle swz) {
  const cuuint32_t ones[3] = {1, 1, 1};
  fn(tm, CU_TENSOR_MAP_DATA_TYPE_BFLOAT16, rank, const_cast<void*>(base), dims, strides, box, ones,
     CU_TENSOR_MAP_INTERLEAVE_NONE, swz, CU_TENSOR_MAP_L2_PROMOTION_L2_128B, CU_TENSOR_MAP_FLOAT_OOB_FILL_NONE);
}

}

extern "C" void kernel_launch(void* const* d_in, const int* in_sizes, int n_in, void* d_out, int out_size) {
  (void)in_sizes; (void)n_in; (void)out_size;
  Params p;
  p.q = (const __nv_bfloat16*)d_in[0];
  p.k = (const __nv_bfloat16*)d_in[1];
  p.v = (const __nv_bfloat16*)d_in[2];
  p.shift_k = (const __nv_bfloat16*)d_in[3];
  p.ssm_k = (const __nv_bfloat16*)d_in[4];
  p.ssm_D = (const __nv_bfloat16*)d_in[5];
  p.wqkv = (const __nv_bfloat16*)d_in[7];
  p.wo = (const __nv_bfloat16*)d_in[8];
  p.gate_w = (const __nv_bfloat16*)d_in[9];
  p.out = (__nv_bfloat16*)d_out;
  p.zero = 0;

  static EncodeFn fn = nullptr;
  static void *yaddr = nullptr, *uaddr = nullptr;
  if (!fn) {
    cudaDriverEntryPointQueryResult qr;
    void* f = nullptr;
    cudaGetDriverEntryPoint("cuTensorMapEncodeTiled", &f, cudaEnableDefault, &qr);
    fn = (EncodeFn)f;
    cudaGetSymbolAddress(&yaddr, g_Y);
    cudaGetSymbolAddress(&uaddr, g_U);
    cudaFuncSetAttribute(fused_kernel, cudaFuncAttributeMaxDynamicSharedMemorySize, SMEM_BYTES);
  }
  Maps m;
  {
    const cuuint64_t dims[3] = {640, 1024, 2}, st[2] = {2560, 1280};
    const cuuint32_t box[3] = {64, 64, 2};
    encode(fn, &m.x, p.q, 3, dims, st, box, CU_TENSOR_MAP_SWIZZLE_128B);
  }
  {
    const cuuint64_t dims[3] = {640, 640, 3}, st[2] = {3840, 1280};
    const cuuint32_t box[3] = {64, 64, 3}, boxt[3] = {16, 64, 3};
    encode(fn, &m.wm, p.wqkv, 3, dims, st, box, CU_TENSOR_MAP_SWIZZLE_128B);
    encode(fn, &m.wt, p.wqkv, 3, dims, st, boxt, CU_TENSOR_MAP_SWIZZLE_32B);
  }
  {
    const cuuint64_t dims[3] = {64, 2048, 10}, st[2] = {1280, 128};
    const cuuint32_t boxk[3] = {64, 35, 1}, boxv[3] = {64, 32, 1};
    encode(fn, &m.k, p.k, 3, dims, st, boxk, CU_TENSOR_MAP_SWIZZLE_128B);
    encode(fn, &m.v, p.v, 3, dims, st, boxv, CU_TENSOR_MAP_SWIZZLE_128B);
  }
  {
    const cuuint64_t dims[3] = {16, 640, 40}, st[2] = {1280, 32};
    const cuuint32_t box[3] = {16, 40, 5};
    encode(fn, &m.wo, p.wo, 3, dims, st, box, CU_TENSOR_MAP_SWIZZLE_32B);
  }
  {
    const cuuint64_t dims[2] = {2048, 640}, st[1] = {Y_PITCH * 16};
    const cuuint32_t box[2] = {64, 80};
    encode(fn, &m.y, yaddr, 2, dims, st, box, CU_TENSOR_MAP_SWIZZLE_128B);
    const cuuint64_t stu[1] = {U_PITCH * 16};
    const cuuint32_t boxu[2] = {32, 64};
    encode(fn, &m.u, uaddr, 2, dims, stu, boxu, CU_TENSOR_MAP_SWIZZLE_NONE);
  }
  {
    const cuuint64_t dims[2] = {640, 2048}, st[1] = {1280};
    const cuuint32_t bqm[2] = {64, 128}, bqt[2] = {16, 128}, bom[2] = {64, 16}, bot[2] = {16, 16};
    encode(fn, &m.qm, p.q, 2, dims, st, bqm, CU_TENSOR_MAP_SWIZZLE_128B);
    encode(fn, &m.qt, p.q, 2, dims, st, bqt, CU_TENSOR_MAP_SWIZZLE_32B);
    encode(fn, &m.om, p.out, 2, dims, st, bom, CU_TENSOR_MAP_SWIZZLE_128B);
    encode(fn, &m.ot, p.out, 2, dims, st, bot, CU_TENSOR_MAP_SWIZZLE_32B);
  }
  fused_kernel<<<NCTA, NTHR, SMEM_BYTES>>>(m, p);
}
```

```cpp
#include <cuda.h>
#include <cuda_bf16.h>
#include <cuda_runtime.h>
#include <stdint.h>

namespace {

constexpr int SEQ = 2048, DIM = 640, NCTA = 128, NTHR = 512;

#define TRIG_KB 9
#define KV_KB 2
#define DEV_EXIT 0
#define ATT_GATE 1
#define G_AFTER 0
#define FENCE_LO 0
#define FENCE_HI 0
#define PW1 2
#define PW2 1
#define ENDBAR 0
#define PAD_KB 0
#define Y_ALIAS 1
#define H_EARLY 1
#define NOMB 0
#define SRC_ROT 0
#define WAIT_NS 0
#define WB_TRIG B_USIG
#define G_POS 0
#define TAILF 1
#define T_ISSUE 384
#define T_PF 416
#define T_INIT 448
#define ATT_MERGE 0
#define BMAP 1
#define PRE2 1
#define O_DEFER 0
#define CH_W2 0
#define HALO_FIRST 1
#define PREV_EARLY 0
#define WS 2
#define SUB0 1
#define ACQ 0
#define U_TMA 0
#define U_GATE 0
#define RF_GATE 0
#define WO_TRIG B_WST
#define WL_TRIG B_WOP
#define WO_GATE 1

constexpr uint32_t STAGE_BYTES = 47104, ST_W = 16384, ST_WT = 40960;
constexpr uint32_t O_BYTES = 20480, WO_BYTES = 12800;
constexpr uint32_t OFF_OA = 0;
constexpr uint32_t OFF_QS = 3 * O_BYTES, OFF_QT = OFF_QS + 16384;
constexpr uint32_t OFF_WC = 81920;
constexpr uint32_t OFF_WA = 94720;
constexpr uint32_t OFF_GATE = 145920;
constexpr uint32_t OFF_KVX = 147968;
constexpr uint32_t OFF_D = OFF_GATE + 512;
constexpr uint32_t OFF_CH3 = 163840;
constexpr uint32_t CH_BYTES = 12288, U_BYTES = 4096;
constexpr uint32_t OFF_FT = 225280, OFF_GT = 229376;
constexpr uint32_t OFF_CH0 = 188416;
constexpr uint32_t OFF_KVS = OFF_CH0, KVS_V = 4480, KVS_BYTES = 8576;
constexpr uint32_t OFF_WS = OFF_WA;
__device__ __forceinline__ uint32_t off_us(int s) { return OFF_CH0 + 4096 * ((0x65320 >> (4 * s)) & 7); }
constexpr uint32_t OFF_YT = 163840;
constexpr uint32_t OFF_BAR = 231936;
constexpr uint32_t SMEM_BYTES = OFF_BAR + 512;

enum : uint32_t {
  B_FULL1 = 0, B_EMPTY1 = 4, B_S3 = 7, B_FULL2 = 52, B_EMPTY2 = 13, B_U = 8, B_GATE = 12, B_HA = 19, B_HB = 20,
  B_ATTN = 21, B_C34 = 22, B_CONV = 23, B_YFULL = 24, B_EPOCH = 25, B_PREP = 26, B_P1 = 27, B_LAST = 28,
  B_E3 = 29, B_OSIG = 30, B_WOP = 31, B_USIG = 32, B_WST = 33, B_KV = 34, B_KVD = 39, B_HC = 61, B_QF = 62, B_YST = 40,
  B_US = 45, B_YSIG = 50
};
constexpr uint32_t OFF_EPOCH = OFF_BAR + 8 * 51;
__device__ __forceinline__ uint32_t off_o(int j) { return j < 4 ? OFF_OA + j * O_BYTES : j < 6 ? OFF_CH0 + (j - 4) * O_BYTES : OFF_OA + (j - 6) * O_BYTES; }
__device__ __forceinline__ uint32_t off_w(int j) { return j < 4 ? OFF_WA + j * WO_BYTES : j == 4 ? OFF_KVX : j == 5 ? OFF_WC : OFF_WA + (j - 6) * WO_BYTES; }
__device__ __forceinline__ int step_src(int hg, int j) { return SRC_ROT ? (hg + j) & 7 : j == 0 ? hg : j <= hg ? j - 1 : j; }
__device__ __forceinline__ bool tail_first(int hg) { return TAILF && (hg & 3) == 3; }
__device__ __forceinline__ uint32_t off_ch(int c) { return (c < 3 ? OFF_CH0 : OFF_CH3 - 3 * CH_BYTES) + c * CH_BYTES; }

#define U_PITCH 264
__device__ __align__(1024) uint4 g_U[DIM * U_PITCH];
__device__ uint4 g_O[NCTA * 1280];
#define g_Y g_U
constexpr int Y_PITCH = U_PITCH;
__device__ uint4 g_WO[64 * 800];
__device__ uint4 g_halo[NCTA * 2 * 7 * 32];
__device__ float g_gate[SEQ + PAD_KB * 256];
__device__ unsigned g_cnt[32 * (1 + 2 * 16 + 8 + NCTA)];
constexpr int C_LAUNCH = 0, C_PREP = 32, C_Y = 32 * 17, C_W = 32 * 33, C_O = 32 * 41;

#define TSM(cond, slot) do { } while (0)
#define TSIF(cond, slot) do { if (__LINE__ >= FENCE_LO && __LINE__ < FENCE_HI) sched_fence(); } while (0)
__device__ __forceinline__ void sched_fence() {
  asm volatile("{\n.reg .pred p;\n.reg .u32 c;\nmov.u32 c, %%clock;\nsetp.eq.u32 p, c, 0;\n@p st.shared.u32 [%0], c;\n}"
               ::"r"(1024 + OFF_EPOCH + 4) : "memory");
}
#define TS(slot) TSIF(true, slot)

struct Params {
  const __nv_bfloat16 *q, *k, *v, *shift_k, *ssm_k, *ssm_D, *wqkv, *wo, *gate_w;
  __nv_bfloat16* out;
  uint32_t zero;
};

#define POLL_NS 0
constexpr int SPIN_LIMIT = 1 << 17;

__device__ __forceinline__ void mbar_init(uint32_t bar, uint32_t count) {
  asm volatile("mbarrier.init.shared::cta.b64 [%0], %1;" ::"r"(bar), "r"(count) : "memory");
}
__device__ __forceinline__ void mbar_expect_tx(uint32_t bar, uint32_t bytes) {
  asm volatile("mbarrier.arrive.expect_tx.shared::cta.b64 _, [%0], %1;" ::"r"(bar), "r"(bytes) : "memory");
}
__device__ __forceinline__ void mbar_arrive(uint32_t bar) {
  asm volatile("mbarrier.arrive.shared::cta.b64 _, [%0];" ::"r"(bar) : "memory");
}
__device__ __forceinline__ void mbar_wait(uint32_t bar, uint32_t parity) {
  uint32_t ok;
  int spins = 0;
  do {
    if (WAIT_NS)
      asm volatile("{\n.reg .pred p;\nmbarrier.try_wait.parity.shared::cta.b64 p, [%1], %2, %3;\nselp.b32 %0, 1, 0, p;\n}"
                   : "=r"(ok) : "r"(bar), "r"(parity), "r"(WAIT_NS) : "memory");
    else
      asm volatile("{\n.reg .pred p;\nmbarrier.try_wait.parity.shared::cta.b64 p, [%1], %2;\nselp.b32 %0, 1, 0, p;\n}"
                   : "=r"(ok) : "r"(bar), "r"(parity) : "memory");
    if (++spins > SPIN_LIMIT) break;
  } while (!ok);
}
__device__ __forceinline__ void flag_poll(const unsigned* p, unsigned target) {
  unsigned v;
  int spins = 0;
  do {
    if (POLL_NS && spins) __nanosleep(POLL_NS);
    asm volatile("ld.relaxed.gpu.global.u32 %0, [%1];" : "=r"(v) : "l"(p) : "memory");
    if (++spins > SPIN_LIMIT) break;
  } while ((int)(v - target) < 0);
}
__device__ __forceinline__ void flag_wait(const unsigned* p, unsigned target) {
  flag_poll(p, target);
  if (ACQ) asm volatile("fence.acquire.gpu;\nfence.proxy.async.global;" ::: "memory");
}
__device__ __forceinline__ void flag_signal(unsigned* p, int n, int lane) {
  if (lane == 0) asm volatile("fence.release.gpu;" ::: "memory");
  __syncwarp();
  if (lane < n) asm volatile("red.relaxed.gpu.global.add.u32 [%0], 1;" ::"l"(p + 32 * lane) : "memory");
}
__device__ __forceinline__ void flag_bump(unsigned* p) {
  asm volatile("red.relaxed.gpu.global.add.u32 [%0], 1;" ::"l"(p) : "memory");
}
__device__ __forceinline__ void fence_async_smem() { asm volatile("fence.proxy.async.shared::cta;" ::: "memory"); }
__device__ __forceinline__ void wg_sync(int id) { asm volatile("bar.sync %0, 128;" ::"r"(id) : "memory"); }

__device__ __forceinline__ void tma_2d(uint32_t dst, const CUtensorMap* tm, int c0, int c1, uint32_t bar) {
  asm volatile("cp.async.bulk.tensor.2d.shared::cluster.global.mbarrier::complete_tx::bytes [%0], [%1, {%3, %4}], [%2];"
               ::"r"(dst), "l"(tm), "r"(bar), "r"(c0), "r"(c1) : "memory");
}
__device__ __forceinline__ void tma_3d(uint32_t dst, const CUtensorMap* tm, int c0, int c1, int c2, uint32_t bar) {
  asm volatile("cp.async.bulk.tensor.3d.shared::cluster.global.mbarrier::complete_tx::bytes [%0], [%1, {%3, %4, %5}], [%2];"
               ::"r"(dst), "l"(tm), "r"(bar), "r"(c0), "r"(c1), "r"(c2) : "memory");
}
__device__ __forceinline__ void bulk_load(uint32_t dst, const void* src, uint32_t bytes, uint32_t bar) {
  asm volatile("cp.async.bulk.shared::cluster.global.mbarrier::complete_tx::bytes [%0], [%1], %2, [%3];"
               ::"r"(dst), "l"(src), "r"(bytes), "r"(bar) : "memory");
}
__device__ __forceinline__ void tm_prefetch(const CUtensorMap* tm) {
  asm volatile("prefetch.tensormap [%0];" ::"l"(tm) : "memory");
}

__device__ __forceinline__ void wg_fence() { asm volatile("wgmma.fence.sync.aligned;" ::: "memory"); }
__device__ __forceinline__ void wg_commit() { asm volatile("wgmma.commit_group.sync.aligned;" ::: "memory"); }
template <int N> __device__ __forceinline__ void wg_wait() { asm volatile("wgmma.wait_group.sync.aligned %0;" ::"n"(N) : "memory"); }
__device__ __forceinline__ uint32_t desc_lo(uint32_t addr, uint32_t lbo) { return ((addr & 0x3FFFF) >> 4) | ((lbo >> 4) << 16); }
constexpr uint32_t desc_hi(uint32_t sbo, uint32_t swz) { return (sbo >> 4) | (swz << 30); }
constexpr uint32_t HI_SW128 = desc_hi(1024, 1), HI_SW64 = desc_hi(512, 2), HI_SW32 = desc_hi(256, 3), HI_NONE = desc_hi(128, 0);
template <int N> __device__ __forceinline__ void pin(float* d) {
#pragma unroll
  for (int i = 0; i < N; i++) asm volatile("" : "+f"(d[i])::"memory");
}

__device__ __forceinline__ uint32_t lds32(uint32_t a) {
  uint32_t v;
  asm volatile("ld.volatile.shared.u32 %0, [%1];" : "=r"(v) : "r"(a) : "memory");
  return v;
}
__device__ __forceinline__ uint4 ldg128(const void* a) {
  uint4 v;
  asm volatile("ld.global.nc.v4.u32 {%0, %1, %2, %3}, [%4];" : "=r"(v.x), "=r"(v.y), "=r"(v.z), "=r"(v.w) : "l"(a) : "memory");
  return v;
}
__device__ __forceinline__ uint2 ldg64(const void* a) {
  uint2 v;
  asm volatile("ld.global.nc.v2.u32 {%0, %1}, [%2];" : "=r"(v.x), "=r"(v.y) : "l"(a) : "memory");
  return v;
}
__device__ __forceinline__ void ldsm4(uint32_t* r, uint32_t a) {
  asm volatile("ldmatrix.sync.aligned.m8n8.x4.shared.b16 {%0, %1, %2, %3}, [%4];"
               : "=r"(r[0]), "=r"(r[1]), "=r"(r[2]), "=r"(r[3]) : "r"(a) : "memory");
}
__device__ __forceinline__ void ldsm4t(uint32_t* r, uint32_t a) {
  asm volatile("ldmatrix.sync.aligned.m8n8.x4.trans.shared.b16 {%0, %1, %2, %3}, [%4];"
               : "=r"(r[0]), "=r"(r[1]), "=r"(r[2]), "=r"(r[3]) : "r"(a) : "memory");
}
__device__ __forceinline__ uint4 lds128(uint32_t a) {
  uint4 v;
  asm volatile("ld.shared.v4.u32 {%0, %1, %2, %3}, [%4];" : "=r"(v.x), "=r"(v.y), "=r"(v.z), "=r"(v.w) : "r"(a) : "memory");
  return v;
}
__device__ __forceinline__ void sts128(uint32_t a, uint32_t x, uint32_t y, uint32_t z, uint32_t w) {
  asm volatile("st.shared.v4.u32 [%0], {%1, %2, %3, %4};" ::"r"(a), "r"(x), "r"(y), "r"(z), "r"(w) : "memory");
}
__device__ __forceinline__ void stsm4(uint32_t a, const uint32_t* r) {
  asm volatile("stmatrix.sync.aligned.m8n8.x4.shared.b16 [%0], {%1, %2, %3, %4};" ::"r"(a), "r"(r[0]), "r"(r[1]), "r"(r[2]), "r"(r[3]) : "memory");
}
__device__ __forceinline__ void stsm4t(uint32_t a, const uint32_t* r) {
  asm volatile("stmatrix.sync.aligned.m8n8.x4.trans.shared.b16 [%0], {%1, %2, %3, %4};" ::"r"(a), "r"(r[0]), "r"(r[1]), "r"(r[2]), "r"(r[3]) : "memory");
}
__device__ __forceinline__ uint32_t pack2(float lo, float hi) {
  uint32_t r;
  asm("cvt.rn.bf16x2.f32 %0, %1, %2;" : "=r"(r) : "f"(hi), "f"(lo));
  return r;
}
__device__ __forceinline__ uint32_t movm(uint32_t a) {
  uint32_t d;
  asm volatile("movmatrix.sync.aligned.m8n8.trans.b16 %0, %1;" : "=r"(d) : "r"(a));
  return d;
}
__device__ __forceinline__ uint32_t bmul(uint32_t a, uint32_t b) {
  uint32_t d;
  asm("mul.rn.bf16x2 %0, %1, %2;" : "=r"(d) : "r"(a), "r"(b));
  return d;
}
__device__ __forceinline__ uint32_t badd(uint32_t a, uint32_t b) {
  uint32_t d;
  asm("add.rn.bf16x2 %0, %1, %2;" : "=r"(d) : "r"(a), "r"(b));
  return d;
}
__device__ __forceinline__ float bf_lo(uint32_t x) { return __uint_as_float(x << 16); }
__device__ __forceinline__ float bf_hi(uint32_t x) { return __uint_as_float(x & 0xFFFF0000u); }
__device__ __forceinline__ float ex2(float x) {
  float y;
  asm("ex2.approx.ftz.f32 %0, %1;" : "=f"(y) : "f"(x));
  return y;
}
__device__ __forceinline__ float rcp(float x) {
  float y;
  asm("rcp.approx.ftz.f32 %0, %1;" : "=f"(y) : "f"(x));
  return y;
}
__device__ __forceinline__ void mma16816(float* d, uint32_t a0, uint32_t a1, uint32_t a2, uint32_t a3, uint32_t b0, uint32_t b1) {
  asm volatile("mma.sync.aligned.m16n8k16.row.col.f32.bf16.bf16.f32 {%0, %1, %2, %3}, {%4, %5, %6, %7}, {%8, %9}, {%0, %1, %2, %3};"
               : "+f"(d[0]), "+f"(d[1]), "+f"(d[2]), "+f"(d[3])
               : "r"(a0), "r"(a1), "r"(a2), "r"(a3), "r"(b0), "r"(b1));
}
__device__ __forceinline__ void mma1688(float* d, uint32_t a0, uint32_t a1, uint32_t b0) {
  asm volatile("mma.sync.aligned.m16n8k8.row.col.f32.bf16.bf16.f32 {%0, %1, %2, %3}, {%4, %5}, {%6}, {%0, %1, %2, %3};"
               : "+f"(d[0]), "+f"(d[1]), "+f"(d[2]), "+f"(d[3])
               : "r"(a0), "r"(a1), "r"(b0));
}

template <int N> struct WgRS;
template <int N> struct WgSST;
template <> struct WgRS<32> {
  template <uint32_t HB>
  static __device__ __forceinline__ void mma(float* d, const uint32_t* a, uint32_t db) {
    asm volatile("{\n.reg .pred p;\n.reg .b64 db;\nsetp.ne.b32 p, %22, 0;\n"
      "mov.b64 db, {%20, %21};\n"
      "wgmma.mma_async.sync.aligned.m64n32k16.f32.bf16.bf16 {"
      "%0, %1, %2, %3, %4, %5, %6, %7, %8, %9, %10, %11, %12, %13, %14, %15"
      "}, {%16, %17, %18, %19}, db, p, 1, 1, 1;\n}\n"
      : "+f"(d[0]), "+f"(d[1]), "+f"(d[2]), "+f"(d[3]), "+f"(d[4]), "+f"(d[5]), "+f"(d[6]), "+f"(d[7]),
        "+f"(d[8]), "+f"(d[9]), "+f"(d[10]), "+f"(d[11]), "+f"(d[12]), "+f"(d[13]), "+f"(d[14]), "+f"(d[15])
      : "r"(a[0]), "r"(a[1]), "r"(a[2]), "r"(a[3]), "r"(db), "n"(HB), "n"(1));
  }
  template <uint32_t HB>
  static __device__ __forceinline__ void set(float* d, const uint32_t* a, uint32_t db) {
    asm volatile("{\n.reg .pred p;\n.reg .b64 db;\nsetp.ne.b32 p, %22, 0;\n"
      "mov.b64 db, {%20, %21};\n"
      "wgmma.mma_async.sync.aligned.m64n32k16.f32.bf16.bf16 {"
      "%0, %1, %2, %3, %4, %5, %6, %7, %8, %9, %10, %11, %12, %13, %14, %15"
      "}, {%16, %17, %18, %19}, db, p, 1, 1, 1;\n}\n"
      : "=f"(d[0]), "=f"(d[1]), "=f"(d[2]), "=f"(d[3]), "=f"(d[4]), "=f"(d[5]), "=f"(d[6]), "=f"(d[7]),
        "=f"(d[8]), "=f"(d[9]), "=f"(d[10]), "=f"(d[11]), "=f"(d[12]), "=f"(d[13]), "=f"(d[14]), "=f"(d[15])
      : "r"(a[0]), "r"(a[1]), "r"(a[2]), "r"(a[3]), "r"(db), "n"(HB), "n"(0));
  }
};
template <> struct WgRS<64> {
  template <uint32_t HB>
  static __device__ __forceinline__ void mma(float* d, const uint32_t* a, uint32_t db) {
    asm volatile("{\n.reg .pred p;\n.reg .b64 db;\nsetp.ne.b32 p, %38, 0;\n"
      "mov.b64 db, {%36, %37};\n"
      "wgmma.mma_async.sync.aligned.m64n64k16.f32.bf16.bf16 {"
      "%0, %1, %2, %3, %4, %5, %6, %7, %8, %9, %10, %11, %12, %13, %14, %15, "
      "%16, %17, %18, %19, %20, %21, %22, %23, %24, %25, %26, %27, %28, %29, %30, %31"
      "}, {%32, %33, %34, %35}, db, p, 1, 1, 1;\n}\n"
      : "+f"(d[0]), "+f"(d[1]), "+f"(d[2]), "+f"(d[3]), "+f"(d[4]), "+f"(d[5]), "+f"(d[6]), "+f"(d[7]),
        "+f"(d[8]), "+f"(d[9]), "+f"(d[10]), "+f"(d[11]), "+f"(d[12]), "+f"(d[13]), "+f"(d[14]), "+f"(d[15]),
        "+f"(d[16]), "+f"(d[17]), "+f"(d[18]), "+f"(d[19]), "+f"(d[20]), "+f"(d[21]), "+f"(d[22]), "+f"(d[23]),
        "+f"(d[24]), "+f"(d[25]), "+f"(d[26]), "+f"(d[27]), "+f"(d[28]), "+f"(d[29]), "+f"(d[30]), "+f"(d[31])
      : "r"(a[0]), "r"(a[1]), "r"(a[2]), "r"(a[3]), "r"(db), "n"(HB), "n"(1));
  }
  template <uint32_t HB>
  static __device__ __forceinline__ void set(float* d, const uint32_t* a, uint32_t db) {
    asm volatile("{\n.reg .pred p;\n.reg .b64 db;\nsetp.ne.b32 p, %38, 0;\n"
      "mov.b64 db, {%36, %37};\n"
      "wgmma.mma_async.sync.aligned.m64n64k16.f32.bf16.bf16 {"
      "%0, %1, %2, %3, %4, %5, %6, %7, %8, %9, %10, %11, %12, %13, %14, %15, "
      "%16, %17, %18, %19, %20, %21, %22, %23, %24, %25, %26, %27, %28, %29, %30, %31"
      "}, {%32, %33, %34, %35}, db, p, 1, 1, 1;\n}\n"
      : "=f"(d[0]), "=f"(d[1]), "=f"(d[2]), "=f"(d[3]), "=f"(d[4]), "=f"(d[5]), "=f"(d[6]), "=f"(d[7]),
        "=f"(d[8]), "=f"(d[9]), "=f"(d[10]), "=f"(d[11]), "=f"(d[12]), "=f"(d[13]), "=f"(d[14]), "=f"(d[15]),
        "=f"(d[16]), "=f"(d[17]), "=f"(d[18]), "=f"(d[19]), "=f"(d[20]), "=f"(d[21]), "=f"(d[22]), "=f"(d[23]),
        "=f"(d[24]), "=f"(d[25]), "=f"(d[26]), "=f"(d[27]), "=f"(d[28]), "=f"(d[29]), "=f"(d[30]), "=f"(d[31])
      : "r"(a[0]), "r"(a[1]), "r"(a[2]), "r"(a[3]), "r"(db), "n"(HB), "n"(0));
  }
};
template <> struct WgSST<48> {
  template <uint32_t HA, uint32_t HB>
  static __device__ __forceinline__ void mma(float* d, uint32_t da, uint32_t db, int sc) {
    asm volatile("{\n.reg .pred p;\n.reg .b64 da, db;\nsetp.ne.b32 p, %28, 0;\n"
      "mov.b64 da, {%24, %25};\nmov.b64 db, {%26, %27};\n"
      "wgmma.mma_async.sync.aligned.m64n48k16.f32.bf16.bf16 {"
      "%0, %1, %2, %3, %4, %5, %6, %7, %8, %9, %10, %11, %12, %13, %14, %15, "
      "%16, %17, %18, %19, %20, %21, %22, %23"
      "}, da, db, p, 1, 1, 0, 1;\n}\n"
      : "+f"(d[0]), "+f"(d[1]), "+f"(d[2]), "+f"(d[3]), "+f"(d[4]), "+f"(d[5]), "+f"(d[6]), "+f"(d[7]),
        "+f"(d[8]), "+f"(d[9]), "+f"(d[10]), "+f"(d[11]), "+f"(d[12]), "+f"(d[13]), "+f"(d[14]), "+f"(d[15]),
        "+f"(d[16]), "+f"(d[17]), "+f"(d[18]), "+f"(d[19]), "+f"(d[20]), "+f"(d[21]), "+f"(d[22]), "+f"(d[23])
      : "r"(da), "n"(HA), "r"(db), "n"(HB), "r"(sc));
  }
};
template <> struct WgSST<80> {
  template <uint32_t HA, uint32_t HB>
  static __device__ __forceinline__ void mma(float* d, uint32_t da, uint32_t db, int sc) {
    asm volatile("{\n.reg .pred p;\n.reg .b64 da, db;\nsetp.ne.b32 p, %44, 0;\n"
      "mov.b64 da, {%40, %41};\nmov.b64 db, {%42, %43};\n"
      "wgmma.mma_async.sync.aligned.m64n80k16.f32.bf16.bf16 {"
      "%0, %1, %2, %3, %4, %5, %6, %7, %8, %9, %10, %11, %12, %13, %14, %15, "
      "%16, %17, %18, %19, %20, %21, %22, %23, %24, %25, %26, %27, %28, %29, %30, %31, "
      "%32, %33, %34, %35, %36, %37, %38, %39"
      "}, da, db, p, 1, 1, 0, 1;\n}\n"
      : "+f"(d[0]), "+f"(d[1]), "+f"(d[2]), "+f"(d[3]), "+f"(d[4]), "+f"(d[5]), "+f"(d[6]), "+f"(d[7]),
        "+f"(d[8]), "+f"(d[9]), "+f"(d[10]), "+f"(d[11]), "+f"(d[12]), "+f"(d[13]), "+f"(d[14]), "+f"(d[15]),
        "+f"(d[16]), "+f"(d[17]), "+f"(d[18]), "+f"(d[19]), "+f"(d[20]), "+f"(d[21]), "+f"(d[22]), "+f"(d[23]),
        "+f"(d[24]), "+f"(d[25]), "+f"(d[26]), "+f"(d[27]), "+f"(d[28]), "+f"(d[29]), "+f"(d[30]), "+f"(d[31]),
        "+f"(d[32]), "+f"(d[33]), "+f"(d[34]), "+f"(d[35]), "+f"(d[36]), "+f"(d[37]), "+f"(d[38]), "+f"(d[39])
      : "r"(da), "n"(HA), "r"(db), "n"(HB), "r"(sc));
  }
};
template <> struct WgSST<192> {
  template <uint32_t HA, uint32_t HB>
  static __device__ __forceinline__ void mma(float* d, uint32_t da, uint32_t db, int sc) {
    asm volatile("{\n.reg .pred p;\n.reg .b64 da, db;\nsetp.ne.b32 p, %100, 0;\n"
      "mov.b64 da, {%96, %97};\nmov.b64 db, {%98, %99};\n"
      "wgmma.mma_async.sync.aligned.m64n192k16.f32.bf16.bf16 {"
      "%0, %1, %2, %3, %4, %5, %6, %7, %8, %9, %10, %11, %12, %13, %14, %15, "
      "%16, %17, %18, %19, %20, %21, %22, %23, %24, %25, %26, %27, %28, %29, %30, %31, "
      "%32, %33, %34, %35, %36, %37, %38, %39, %40, %41, %42, %43, %44, %45, %46, %47, "
      "%48, %49, %50, %51, %52, %53, %54, %55, %56, %57, %58, %59, %60, %61, %62, %63, "
      "%64, %65, %66, %67, %68, %69, %70, %71, %72, %73, %74, %75, %76, %77, %78, %79, "
      "%80, %81, %82, %83, %84, %85, %86, %87, %88, %89, %90, %91, %92, %93, %94, %95"
      "}, da, db, p, 1, 1, 0, 1;\n}\n"
      : "+f"(d[0]), "+f"(d[1]), "+f"(d[2]), "+f"(d[3]), "+f"(d[4]), "+f"(d[5]), "+f"(d[6]), "+f"(d[7]),
        "+f"(d[8]), "+f"(d[9]), "+f"(d[10]), "+f"(d[11]), "+f"(d[12]), "+f"(d[13]), "+f"(d[14]), "+f"(d[15]),
        "+f"(d[16]), "+f"(d[17]), "+f"(d[18]), "+f"(d[19]), "+f"(d[20]), "+f"(d[21]), "+f"(d[22]), "+f"(d[23]),
        "+f"(d[24]), "+f"(d[25]), "+f"(d[26]), "+f"(d[27]), "+f"(d[28]), "+f"(d[29]), "+f"(d[30]), "+f"(d[31]),
        "+f"(d[32]), "+f"(d[33]), "+f"(d[34]), "+f"(d[35]), "+f"(d[36]), "+f"(d[37]), "+f"(d[38]), "+f"(d[39]),
        "+f"(d[40]), "+f"(d[41]), "+f"(d[42]), "+f"(d[43]), "+f"(d[44]), "+f"(d[45]), "+f"(d[46]), "+f"(d[47]),
        "+f"(d[48]), "+f"(d[49]), "+f"(d[50]), "+f"(d[51]), "+f"(d[52]), "+f"(d[53]), "+f"(d[54]), "+f"(d[55]),
        "+f"(d[56]), "+f"(d[57]), "+f"(d[58]), "+f"(d[59]), "+f"(d[60]), "+f"(d[61]), "+f"(d[62]), "+f"(d[63]),
        "+f"(d[64]), "+f"(d[65]), "+f"(d[66]), "+f"(d[67]), "+f"(d[68]), "+f"(d[69]), "+f"(d[70]), "+f"(d[71]),
        "+f"(d[72]), "+f"(d[73]), "+f"(d[74]), "+f"(d[75]), "+f"(d[76]), "+f"(d[77]), "+f"(d[78]), "+f"(d[79]),
        "+f"(d[80]), "+f"(d[81]), "+f"(d[82]), "+f"(d[83]), "+f"(d[84]), "+f"(d[85]), "+f"(d[86]), "+f"(d[87]),
        "+f"(d[88]), "+f"(d[89]), "+f"(d[90]), "+f"(d[91]), "+f"(d[92]), "+f"(d[93]), "+f"(d[94]), "+f"(d[95])
      : "r"(da), "n"(HA), "r"(db), "n"(HB), "r"(sc));
  }
};

struct FftConst {
  uint32_t f[2][4], fi[4][4];
  float ta[4], tb[4];
};
__device__ __forceinline__ void cis(int m, float scale, float& c, float& s) {
  const float a = (float)m * (-6.283185307179586f * scale);
  c = __cosf(a);
  s = __sinf(a);
}
__device__ __forceinline__ void fft_tables(uint32_t (&v)[12], int tw) {
  const int row = tw >> 2, ch = tw & 3;
#pragma unroll
  for (int i = 0; i < 4; i++) {
    float c[2], s[2], x[2];
#pragma unroll
    for (int e = 0; e < 2; e++) {
      cis((((32 * (8 * ch + 2 * i + e) + 15) * (4 * row - 63) + 2048) & 4095) - 2048, 1.f / 4096, c[e], s[e]);
      float gc, gs;
      cis((((row & 15) * (8 * (ch & 1) + 2 * i + e) + 8) & 15) - 8, 1.f / 16, gc, gs);
      x[e] = (row >> 4) == (ch >> 1) ? gc : (ch >> 1) ? gs : -gs;
    }
    v[i] = pack2(c[0] * 0.125f, c[1] * 0.125f);
    v[4 + i] = pack2(s[0] * 0.125f, s[1] * 0.125f);
    v[8 + i] = pack2(x[0], x[1]);
  }
#pragma unroll
  for (int i = 0; i < 12; i++) asm volatile("" : "+r"(v[i]));
}
__device__ __forceinline__ void fft_tables_store(const uint32_t (&v)[12], uint32_t sb, int tw) {
  const int row = tw >> 2;
  const uint32_t x = ((tw ^ (row >> 1)) & 3) << 4, a = sb + OFF_FT + (16 * (row >> 3) + (row & 7)) * 64 + x;
  sts128(a, v[0], v[1], v[2], v[3]);
  sts128(a + 512, v[4], v[5], v[6], v[7]);
  sts128(sb + OFF_GT + row * 64 + x, v[8], v[9], v[10], v[11]);
}
__device__ __forceinline__ void fft_twiddles(FftConst& k, int w, int lane) {
#pragma unroll
  for (int i = 0; i < 4; i++) {
    float c, s;
    cis((2 * (8 * (i >> 1) + 2 * (lane & 3) + (i & 1)) - 15) * (4 * (8 * w + (lane >> 2)) - 63), 1.f / 4096, c, s);
    k.ta[i] = __fdividef(-s, 1.f + c);
    k.tb[i] = s;
  }
  pin<4>(k.ta);
  pin<4>(k.tb);
}
__device__ __forceinline__ void fft_matrices(FftConst& k, uint32_t sb, int w, int lane) {
  const uint32_t x = (lane >> 1) & 3;
#pragma unroll
  for (int i = 0; i < 2; i++) {
    ldsm4(k.f[i], sb + OFF_FT + (16 * w + (lane & 15)) * 64 + (((2 * i + (lane >> 4)) ^ x) << 4));
    ldsm4t(k.fi[i], sb + OFF_FT + (32 * i + lane) * 64 + ((w ^ x) << 4));
#pragma unroll
    for (int j = 0; j < 4; j++) {
      k.fi[2 + i][j] = (j & 1) ? k.fi[i][j - 1] ^ 0x80008000u : k.fi[i][j + 1];
      asm volatile("" : "+r"(k.fi[2 + i][j]));
    }
  }
}
template <bool INV> __device__ __forceinline__ void rot(float& x, float& y, float a, float b) {
  x = fmaf(INV ? -a : a, y, x);
  y = fmaf(INV ? -b : b, x, y);
  x = fmaf(INV ? -a : a, y, x);
}
__device__ __forceinline__ void twiddle_fwd(uint32_t (&a)[4][4], float* d, const FftConst& k) {
#pragma unroll
  for (int q = 0; q < 4; q++)
#pragma unroll
    for (int j = 0; j < 2; j++) {
      float* x = d + 8 * q + 4 * j;
      rot<false>(x[0], x[2], k.ta[2 * j], k.tb[2 * j]);
      rot<false>(x[1], x[3], k.ta[2 * j + 1], k.tb[2 * j + 1]);
      a[q & 2][2 * j + (q & 1)] = pack2(x[0], x[1]);
      a[(q & 2) + 1][2 * j + (q & 1)] = pack2(x[2], x[3]);
    }
}
__device__ __forceinline__ void g_step(float* d, const uint32_t (&a)[4][4], uint32_t dre, uint32_t dim) {
  WgRS<32>::set<HI_SW64>(d, a[0], dre);
  WgRS<32>::set<HI_SW64>(d + 16, a[2], dre);
  WgRS<32>::mma<HI_SW64>(d, a[1], dim);
  WgRS<32>::mma<HI_SW64>(d + 16, a[3], dim);
  wg_commit();
}

__device__ __forceinline__ void conv_channel(const FftConst& k, uint32_t sb, int c, int wg, int w, int lane) {
  const uint32_t cb = sb + off_ch(c), bars = sb + OFF_BAR;
  const uint32_t du = desc_lo(cb, 1024), dg = desc_lo(sb + OFF_GT, 16), dz = desc_lo(cb + U_BYTES, 16);
  float U[32], H[32];
  uint32_t a[4][4], e[4][4];
  const float dv = __uint_as_float(lds32(sb + OFF_D + 4 * c));
  wg_fence();
  WgRS<64>::set<HI_SW32>(H, k.f[0], du + 256);
  WgRS<64>::mma<HI_SW32>(H, k.f[1], du + 256 + 32);
  wg_commit();
  wg_wait<0>();
  pin<32>(H);
  twiddle_fwd(a, H, k);
  if (ATT_GATE && H_EARLY) mbar_wait(bars + 8 * B_ATTN, 0);
  mbar_wait(bars + 8 * (B_U + (c < 3 ? c : 3)), 0);
  TSM(w == 0 && c < 3, 7 + wg);
  wg_fence();
  WgRS<64>::set<HI_SW32>(U, k.f[0], du);
  WgRS<64>::mma<HI_SW32>(U, k.f[1], du + 32);
  wg_commit();
  g_step(H, a, dg, dg + 64);
  wg_wait<1>();
  pin<32>(U);
  twiddle_fwd(e, U, k);
  wg_fence();
  g_step(U, e, dg, dg + 64);
  wg_wait<0>();
  pin<32>(U);
  pin<32>(H);
#pragma unroll
  for (int j = 0; j < 2; j++) {
    float pr[4][2], pi[4][2];
#pragma unroll
    for (int x = 0; x < 2; x++) {
      H[4 * j + x] += dv;
#pragma unroll
      for (int m = 0; m < 4; m++) {
#pragma unroll
        for (int q = 0; q <= m; q++) {
          const int ih = 16 * (q >> 1) + 2 * (q & 1) + 4 * j + x, iu = 16 * ((m - q) >> 1) + 2 * ((m - q) & 1) + 4 * j + x;
          pr[m][x] = q ? fmaf(H[ih], U[iu], pr[m][x]) : H[ih] * U[iu];
          pi[m][x] = q ? fmaf(H[ih], U[iu + 8], pi[m][x]) : H[ih] * U[iu + 8];
          pr[m][x] = fmaf(-H[ih + 8], U[iu + 8], pr[m][x]);
          pi[m][x] = fmaf(H[ih + 8], U[iu], pi[m][x]);
        }
      }
    }
#pragma unroll
    for (int m = 0; m < 4; m++) {
      a[m & 2][2 * j + (m & 1)] = pack2(pr[m][0], pr[m][1]);
      a[(m & 2) + 1][2 * j + (m & 1)] = pack2(pi[m][0], pi[m][1]);
    }
  }
  wg_fence();
  g_step(U, a, dg + 64, dg);
  const uint32_t za = cb + U_BYTES + (8 * w + (lane & 7)) * 128 + (((lane >> 3) ^ (lane & 7)) << 4);
  const uint32_t ya = cb + (lane >> 4) * 1024 + (8 * w + (lane & 7)) * 32 + ((((lane >> 3) ^ (lane >> 2)) & 1) << 4);
  wg_sync(1 + wg);
  wg_wait<0>();
  pin<32>(U);
  TSIF(w == 0, 80 + c);
#pragma unroll
  for (int p = 0; p < 2; p++) {
#pragma unroll
    for (int i = 0; i < 4; i++) {
      const int j = i & 1;
      float* x = U + 16 * p + 4 * j + (i & 2);
      rot<true>(x[8], x[0], k.ta[2 * j], k.tb[2 * j]);
      rot<true>(x[9], x[1], k.ta[2 * j + 1], k.tb[2 * j + 1]);
      e[p][i] = pack2(x[8], x[9]);
      e[2 + p][i] = pack2(x[0], x[1]);
    }
    stsm4(za ^ (64 * p), e[p]);
    stsm4((za ^ (64 * p)) + 4096, e[2 + p]);
  }
  fence_async_smem();
  wg_sync(1 + wg);
  wg_fence();
  WgRS<64>::set<HI_SW128>(H, k.fi[0], dz);
#pragma unroll
  for (int ks = 1; ks < 4; ks++) WgRS<64>::mma<HI_SW128>(H, k.fi[ks], dz + 128 * ks);
  wg_commit();
  wg_wait<0>();
  pin<32>(H);
  TSIF(w == 0, 88 + c);
#pragma unroll
  for (int j = 0; j < 8; j++)
    a[j >> 2][j & 3] = j < 2 ? pack2(H[4 * j], H[4 * j + 1]) : pack2(H[4 * j] + H[4 * j - 6], H[4 * j + 1] + H[4 * j - 5]);
  stsm4(ya, a[0]);
  stsm4(ya + 2048, a[1]);
  fence_async_smem();
  __syncwarp();
}

__device__ __forceinline__ void prep_slab(uint4* res, const uint2* sw, uint32_t sb, int slab, int w, int lane) {
  const int t = lane & 3, tp = (lane & 7) >> 1, pos = 8 * tp + 2 * (((lane >> 3) + tp) & 3) + (lane & 1);
  const uint32_t base = sb + OFF_KVS + slab * KVS_BYTES + pos * 128;
  uint32_t kk[2][4][4], vv[2][4];
  mbar_wait(sb + OFF_BAR + 8 * (B_KV + slab), 0);
#pragma unroll
  for (int h = 0; h < 2; h++) {
#pragma unroll
    for (int j = 0; j < 4; j++) {
      const uint32_t a = base + 128 * j;
      ldsm4t(kk[h][j], a + (((w + 4 * h) ^ ((a >> 7) & 7)) << 4));
    }
    const uint32_t a = base + KVS_V;
    ldsm4t(vv[h], a + (((w + 4 * h) ^ ((a >> 7) & 7)) << 4));
  }
#pragma unroll
  for (int h = 0; h < 2; h++) {
    uint32_t (&k)[4][4] = kk[h];
    uint32_t (&v)[4] = vv[h];
    const uint32_t w0 = __byte_perm(sw[h].x, 0, 0x1010), w1 = __byte_perm(sw[h].x, 0, 0x3232);
    const uint32_t w2 = __byte_perm(sw[h].y, 0, 0x1010), w3 = __byte_perm(sw[h].y, 0, 0x3232);
#pragma unroll
    for (int m = 0; m < 4; m++)
      v[m] = bmul(badd(badd(badd(bmul(k[0][m], w3), bmul(k[1][m], w2)), bmul(k[2][m], w1)), bmul(k[3][m], w0)), v[m]);
    uint32_t a[4];
#pragma unroll
    for (int m = 0; m < 4; m++) a[m] = (t & 1) ? v[(m + 3) & 3] : v[m];
    res[h] = (t & 2) ? make_uint4(a[2], a[3], a[0], a[1]) : make_uint4(a[0], a[1], a[2], a[3]);
  }
}

__device__ __forceinline__ void prep_gate(const Params& p, int b, int w, int lane) {
  uint2 gw[5], x[4][5];
#pragma unroll
  for (int j = 0; j < 5; j++) gw[j] = ldg64(reinterpret_cast<const uint2*>(p.gate_w) + lane + 32 * j);
#pragma unroll
  for (int i = 0; i < 4; i++)
#pragma unroll
    for (int j = 0; j < 5; j++)
      x[i][j] = ldg64(reinterpret_cast<const uint2*>(p.q) + (16 * b + 4 * w + i) * (DIM / 4) + lane + 32 * j);
  float s[4];
#pragma unroll
  for (int i = 0; i < 4; i++) {
    s[i] = 0.f;
#pragma unroll
    for (int j = 0; j < 5; j++) {
      const uint32_t m0 = bmul(x[i][j].x, gw[j].x), m1 = bmul(x[i][j].y, gw[j].y);
      s[i] += (bf_lo(m0) + bf_hi(m0)) + (bf_lo(m1) + bf_hi(m1));
    }
  }
  const bool h = lane & 16, q = lane & 8;
  const float a = (h ? s[2] : s[0]) + __shfl_xor_sync(0xffffffffu, h ? s[0] : s[2], 16);
  const float c = (h ? s[3] : s[1]) + __shfl_xor_sync(0xffffffffu, h ? s[1] : s[3], 16);
  float z = (q ? c : a) + __shfl_xor_sync(0xffffffffu, q ? a : c, 8);
#pragma unroll
  for (int o = 4; o > 0; o >>= 1) z += __shfl_xor_sync(0xffffffffu, z, o);
  z = bf_lo(pack2(z, 0.f));
  if ((lane & 7) == 0) g_gate[16 * b + 4 * w + (lane >> 3)] = bf_lo(pack2(__fdividef(1.f, 1.f + __expf(-z)), 0.f));
}

__device__ __forceinline__ uint32_t bmax(uint32_t a, uint32_t b) {
  uint32_t d;
  asm("max.bf16x2 %0, %1, %2;" : "=r"(d) : "r"(a), "r"(b));
  return d;
}
__device__ __forceinline__ void softmax_two(const float (&l)[2][2], uint32_t& p0, uint32_t& p1) {
  constexpr float kScale = 0.22360679774997896f, kLog2e = 1.4426950408889634f;
  const uint32_t r0 = pack2(l[0][0], l[1][0]), r1 = pack2(l[0][1], l[1][1]);
  const uint32_t x0 = pack2(bf_lo(r0) * kScale, bf_hi(r0) * kScale), x1 = pack2(bf_lo(r1) * kScale, bf_hi(r1) * kScale);
  uint32_t m = bmax(x0, x1);
  m = bmax(m, __shfl_xor_sync(0xffffffffu, m, 1));
  m = bmax(m, __shfl_xor_sync(0xffffffffu, m, 2));
  const float m0 = bf_lo(m) * kLog2e, m1 = bf_hi(m) * kLog2e;
  p0 = pack2(ex2(bf_lo(x0) * kLog2e - m0), ex2(bf_lo(x1) * kLog2e - m0));
  p1 = pack2(ex2(bf_hi(x0) * kLog2e - m1), ex2(bf_hi(x1) * kLog2e - m1));
}

__device__ __forceinline__ void halo_read(uint32_t (&kpv)[10], uint32_t (&vpv)[10], uint32_t (&tg)[7], const uint4* hp) {
#pragma unroll
  for (int j = 0; j < 7; j++) {
    uint32_t x0, x1, x2;
    asm volatile("ld.relaxed.gpu.global.v4.u32 {%0, %1, %2, %3}, [%4];"
                 : "=r"(x0), "=r"(x1), "=r"(x2), "=r"(tg[j]) : "l"(hp + 32 * j) : "memory");
    if (j < 4) kpv[3 * j] = x0; else vpv[3 * j - 10] = x0;
    if (j < 3) kpv[3 * j + 1] = x1; else vpv[3 * j - 9] = x1;
    if (j < 3) kpv[3 * j + 2] = x2; else if (j < 6) vpv[3 * j - 8] = x2;
  }
}

template <int ROT>
__device__ __forceinline__ void pack_qkv(const float* acc, uint32_t (&qlo)[10], uint32_t (&qhi)[10], uint32_t (&klo)[10],
                                         uint32_t (&khi)[10], uint32_t (&vlo)[10], uint32_t (&vhi)[10]) {
#pragma unroll
  for (int j = 0; j < 10; j++) {
    const int x = (j + ROT) % 10, tq = x < 8 ? x : 16 + x, tk = x < 8 ? 8 + x : 18 + x, tv = x < 8 ? 16 + x : 20 + x;
    khi[j] = pack2(acc[4 * tk + 2], acc[4 * tk + 3]);
    vhi[j] = movm(pack2(acc[4 * tv + 2], acc[4 * tv + 3]));
    qlo[j] = pack2(acc[4 * tq], acc[4 * tq + 1]);
    qhi[j] = pack2(acc[4 * tq + 2], acc[4 * tq + 3]);
    klo[j] = pack2(acc[4 * tk], acc[4 * tk + 1]);
    vlo[j] = pack2(acc[4 * tv], acc[4 * tv + 1]);
    asm volatile("" : "+r"(khi[j]), "+r"(qlo[j]), "+r"(qhi[j]), "+r"(klo[j]), "+r"(vlo[j]));
  }
}

template <int ROT> __device__ __forceinline__ void halo_send(const float* acc, uint4* ho, uint32_t tag) {
#pragma unroll
  for (int j = 0; j < 7; j++) {
    uint32_t x[3];
#pragma unroll
    for (int e = 0; e < 3; e++) {
      const int i = 3 * j + e, y = (i % 10 + ROT) % 10, tk = y < 8 ? 8 + y : 18 + y, tv = y < 8 ? 16 + y : 20 + y;
      x[e] = i < 10 ? pack2(acc[4 * tk + 2], acc[4 * tk + 3]) : i < 20 ? movm(pack2(acc[4 * tv + 2], acc[4 * tv + 3])) : 0u;
    }
    asm volatile("st.relaxed.gpu.global.v4.u32 [%0], {%1, %2, %3, %4};" ::"l"(ho + 32 * j), "r"(x[0]), "r"(x[1]), "r"(x[2]), "r"(tag) : "memory");
  }
}

__device__ __forceinline__ void attention(float* acc, uint32_t sb, int b, int par, int w, int lane, uint32_t tag) {
  const int g = lane >> 2, t = lane & 3;
  uint32_t klo[10], khi[10], vlo[10], vhi[10], qlo[10], qhi[10], kpv[10], vpv[10];
  if (HALO_FIRST && w == 3 && b < NCTA - 8) {
    uint4* ho = g_halo + (b * 2 + par) * 224 + lane;
    if (tail_first(b & 7)) halo_send<8>(acc, ho, tag);
    else halo_send<0>(acc, ho, tag);
    TSIF(par == 0, 76);
    pin<120>(acc);
  }
  if (tail_first(b & 7)) pack_qkv<8>(acc, qlo, qhi, klo, khi, vlo, vhi);
  else pack_qkv<0>(acc, qlo, qhi, klo, khi, vlo, vhi);
  const uint32_t xa = sb + OFF_KVX + (par * 3) * 2560 + lane * 16;
  if (w < 3) {
    sts128(xa + w * 2560, khi[0], khi[1], khi[2], khi[3]);
    sts128(xa + w * 2560 + 512, khi[4], khi[5], khi[6], khi[7]);
    sts128(xa + w * 2560 + 1024, khi[8], khi[9], vhi[0], vhi[1]);
    sts128(xa + w * 2560 + 1536, vhi[2], vhi[3], vhi[4], vhi[5]);
    sts128(xa + w * 2560 + 2048, vhi[6], vhi[7], vhi[8], vhi[9]);
  } else if (!HALO_FIRST && b < NCTA - 8) {
    uint4* ho = g_halo + (b * 2 + par) * 224 + lane;
#pragma unroll
    for (int j = 0; j < 7; j++) {
      const uint32_t x0 = j < 4 ? khi[3 * j] : vhi[3 * j - 10], x1 = j < 3 ? khi[3 * j + 1] : vhi[3 * j - 9];
      const uint32_t x2 = j < 3 ? khi[3 * j + 2] : j < 6 ? vhi[3 * j - 8] : 0u;
      asm volatile("st.relaxed.gpu.global.v4.u32 [%0], {%1, %2, %3, %4};" ::"l"(ho + 32 * j), "r"(x0), "r"(x1), "r"(x2), "r"(tag) : "memory");
    }
  }
  TSIF(par == 0 && w == 1, 64);
  TSIF(par == 0 && w == 3 && !HALO_FIRST, 76);
#pragma unroll
  for (int j = 0; j < 10; j++) vlo[j] = movm(vlo[j]);
  const bool far0 = 2 * t > g, far1 = 2 * t + 1 > g;
  const uint32_t mfar = (far0 ? 0x0000FFFFu : 0u) | (far1 ? 0xFFFF0000u : 0u);
  float slo[4][2], shi[4][2], lg[2][2];
  uint32_t phi[4], plo[4], qml[4], qmh[4];
#pragma unroll
  for (int h = 0; h < 4; h++) {
    const int f = h == 0 ? 0 : h == 1 ? 3 : h == 2 ? 5 : 8, hf = h < 2 ? 2 : 7;
    const bool mine = (h & 1) ? t >= 2 : t < 2;
    qml[h] = mine ? qlo[hf] : 0u;
    qmh[h] = mine ? qhi[hf] : 0u;
    float a[4] = {0.f, 0.f, 0.f, 0.f}, c[4] = {0.f, 0.f, 0.f, 0.f};
    mma16816(a, qlo[f], qhi[f], qlo[f + 1], qhi[f + 1], klo[f], klo[f + 1]);
    mma16816(c, qlo[f], qhi[f], qlo[f + 1], qhi[f + 1], khi[f], khi[f + 1]);
    mma1688(a, qml[h], qmh[h], klo[hf]);
    mma1688(c, qml[h], qmh[h], khi[hf]);
    slo[h][0] = a[0];
    slo[h][1] = a[1];
    shi[h][0] = lg[h & 1][0] = far0 ? a[2] : c[2];
    shi[h][1] = lg[h & 1][1] = far1 ? a[3] : c[3];
    if (!ATT_MERGE && (h & 1)) softmax_two(lg, phi[h - 1], phi[h]);
  }
  TSIF(par == 0 && w == 1, 65);
  wg_sync(1 + par);
  TSIF(par == 0 && w == 1, 66);
  const bool nohist = (w == 0) && (b < 8);
  const uint4* hp = g_halo + ((b - 8) * 2 + par) * 224 + lane;
  uint32_t tg[7];
  if (w > 0) {
    const uint4 v0 = lds128(xa + (w - 1) * 2560), v1 = lds128(xa + (w - 1) * 2560 + 512), v2 = lds128(xa + (w - 1) * 2560 + 1024);
    const uint4 v3 = lds128(xa + (w - 1) * 2560 + 1536), v4 = lds128(xa + (w - 1) * 2560 + 2048);
    kpv[0] = v0.x; kpv[1] = v0.y; kpv[2] = v0.z; kpv[3] = v0.w; kpv[4] = v1.x; kpv[5] = v1.y; kpv[6] = v1.z; kpv[7] = v1.w;
    kpv[8] = v2.x; kpv[9] = v2.y; vpv[0] = v2.z; vpv[1] = v2.w; vpv[2] = v3.x; vpv[3] = v3.y; vpv[4] = v3.z; vpv[5] = v3.w;
    vpv[6] = v4.x; vpv[7] = v4.y; vpv[8] = v4.z; vpv[9] = v4.w;
  } else if (nohist) {
#pragma unroll
    for (int j = 0; j < 10; j++) kpv[j] = vpv[j] = 0u;
  } else {
    TSIF(par == 0, 77);
    halo_read(kpv, vpv, tg, hp);
  }
  if (w == 0 && !nohist) {
    int spins = 0;
    while (true) {
      bool ok = true;
#pragma unroll
      for (int j = 0; j < 7; j++) ok = ok && tg[j] == tag;
      if (__all_sync(0xffffffffu, ok) || ++spins > SPIN_LIMIT) break;
      halo_read(kpv, vpv, tg, hp);
    }
    TSIF(par == 0, 79);
  }
#pragma unroll
  for (int h = 0; h < 4; h++) {
    const int f = h == 0 ? 0 : h == 1 ? 3 : h == 2 ? 5 : 8, hf = h < 2 ? 2 : 7;
    float a[4] = {0.f, 0.f, 0.f, 0.f};
    mma16816(a, qlo[f], qhi[f], qlo[f + 1], qhi[f + 1], kpv[f], kpv[f + 1]);
    mma1688(a, qml[h], qmh[h], kpv[hf]);
    const float ninf = __int_as_float(0xff800000);
    lg[h & 1][0] = far0 ? (nohist ? ninf : a[0]) : slo[h][0];
    lg[h & 1][1] = far1 ? (nohist ? ninf : a[1]) : slo[h][1];
    if (h & 1) {
      softmax_two(lg, plo[h - 1], plo[h]);
      if (ATT_MERGE) {
        const float lh[2][2] = {{shi[h - 1][0], shi[h - 1][1]}, {shi[h][0], shi[h][1]}};
        softmax_two(lh, phi[h - 1], phi[h]);
      }
    }
  }
  TSIF(par == 0 && w <= 1, 67 + w);
  uint32_t ov[20];
#pragma unroll
  for (int hp = 0; hp < 2; hp++) {
    const int hf = hp ? 7 : 2;
    float sh[4] = {0.f, 0.f, 0.f, 0.f}, i0 = 0.f, i1 = 0.f;
#pragma unroll
    for (int e = 0; e < 2; e++) {
      const int h = 2 * hp + e, f = h == 0 ? 0 : h == 1 ? 3 : h == 2 ? 5 : 8;
      const uint32_t a0 = plo[h] & mfar, a2 = plo[h] & ~mfar, a3 = phi[h] & mfar, c1 = phi[h] & ~mfar;
      float sum[4] = {0.f, 0.f, 0.f, 0.f};
      mma1688(sum, plo[h], phi[h], 0x3F803F80u);
      const float r0 = rcp(sum[0]), r1 = rcp(sum[2]);
#pragma unroll
      for (int j = f; j < f + 2; j++) {
        float o[4] = {0.f, 0.f, 0.f, 0.f};
        mma16816(o, a0, 0u, a2, a3, vpv[j], vlo[j]);
        mma1688(o, 0u, c1, vhi[j]);
        ov[2 * j] = pack2(o[0] * r0, o[1] * r0);
        ov[2 * j + 1] = pack2(o[2] * r1, o[3] * r1);
      }
      const bool mine = e ? g >= 4 : g < 4;
      mma16816(sh, a0, 0u, a2, a3, mine ? vpv[hf] : 0u, mine ? vlo[hf] : 0u);
      mma1688(sh, 0u, c1, mine ? vhi[hf] : 0u);
      if (e == 0 || t >= 2) {
        i0 = r0;
        i1 = r1;
      }
    }
    ov[2 * hf] = pack2(sh[0] * i0, sh[1] * i0);
    ov[2 * hf + 1] = pack2(sh[2] * i1, sh[3] * i1);
  }
  TS(32 + 4 * par + w);
  mbar_wait(sb + OFF_BAR + 8 * B_P1, 0);
  const uint32_t oa = sb + OFF_OA + (lane >> 4) * 2048 + (32 * w + 2 * (lane & 15) + par) * 16;
#pragma unroll
  for (int j = 0; j < 5; j++) stsm4(oa + 4096 * j, ov + 4 * j);
  TSIF(par == 0 && w == 0, 120);
  fence_async_smem();
  TSIF(par == 0 && w == 0, 121);
  __syncwarp();
  if (lane == 0) mbar_arrive(sb + OFF_BAR + 8 * B_ATTN);
  TSIF(par == 0 && w == 0, 122);
}

struct Maps {
  CUtensorMap x, wm, wt, k, v, y, wo, qm, qt, om, ot, u;
};

__device__ __forceinline__ constexpr uint32_t sub_bar(int h) { return h == 0 ? 17 : h == 1 ? 18 : 23; }
__device__ __forceinline__ void load_stage(uint32_t sb, int kb, int b, const Maps& m) {
  const uint32_t st = sb + (kb & 3) * STAGE_BYTES, bar = sb + OFF_BAR + 8 * (B_FULL1 + (kb & 3));
  const int r = b >> 3, hg = b & 7, slab = kb - KV_KB;
  const bool kv = slab >= 0 && slab < 5;
  const uint32_t kbar = sb + OFF_BAR + 8 * (B_KV + slab), dst = sb + OFF_KVS + slab * KVS_BYTES;
  const int cm = 80 * hg + (tail_first(hg) ? 16 : 0), ct = 80 * hg + (tail_first(hg) ? 0 : 64);
  constexpr uint32_t PB = (STAGE_BYTES - ST_W) / WS;
  const bool sub = SUB0 && kb == 0;
  if (!sub) mbar_expect_tx(bar, STAGE_BYTES);
  if (kv) mbar_expect_tx(kbar, KVS_BYTES);
#pragma unroll
  for (int h = 0; h < WS; h++) {
    const uint32_t pb = sub && h < WS - 1 ? sb + OFF_BAR + 8 * sub_bar(h) : bar;
    if (sub) mbar_expect_tx(pb, h ? PB : PB + ST_W);
    if (h == 0) tma_3d(st, &m.x, 64 * kb, 64 * r, 0, pb);
    tma_3d(st + ST_W + 24576 / WS * h, &m.wm, cm, 64 * kb + 64 / WS * h, 0, pb);
    tma_3d(st + ST_WT + 6144 / WS * h, &m.wt, ct, 64 * kb + 64 / WS * h, 0, pb);
  }
  if (kv) tma_3d(dst, &m.k, 0, 32 * (b >> 1) - 3, 2 * slab + (b & 1), kbar);
  if (kv) tma_3d(dst + KVS_V, &m.v, 0, 32 * (b >> 1), 2 * slab + (b & 1), kbar);
}

__global__ void __launch_bounds__(NTHR, 1) fused_kernel(const __grid_constant__ Maps m, const Params p) {
  extern __shared__ __align__(1024) uint8_t smem[];
  const uint32_t sb = (uint32_t)__cvta_generic_to_shared(smem);
  const uint32_t bars = sb + OFF_BAR;
  const int tid = threadIdx.x, lane = tid & 31;
  int b = blockIdx.x;
  if (BMAP == 1) b = (((b & 63) >> 3) * 2 + (b & 1)) * 8 + (((b < 64 ? 0x6521 : 0x7430) >> (4 * ((b >> 1) & 3))) & 7);
  if (BMAP == 2) b = ((b & 63) >> 2) * 8 + (((b < 64 ? 0x6521 : 0x7430) >> (4 * (b & 3))) & 7);
  if (BMAP == 3) b = (((b & 63) >> 3) * 2 + (b & 1)) * 8 + (((b < 64 ? 0x7430 : 0x6521) >> (4 * ((b >> 1) & 3))) & 7);
  if (BMAP == 4) b = (((b >> 4) * 2 + (b & 1)) * 8) + ((b >> 1) & 7);
  if (BMAP == 5) b = 127 - b;
  const int r = b >> 3, hg = b & 7;

  if (tid == T_ISSUE) {
    TSM(true, 0);
#pragma unroll
    for (int i = 0; i < 4; i++) mbar_init(bars + 8 * (B_FULL1 + i), 1);
#pragma unroll
    for (int i = 0; i < 3; i++) mbar_init(bars + 8 * (B_KV + i), 1);
#pragma unroll
    for (int i = 0; i < WS - 1; i++) mbar_init(bars + 8 * sub_bar(i), 1);
    fence_async_smem();
#pragma unroll 1
    for (int kb = 0; kb <= PRE2; kb++) load_stage(sb, kb, b, m);
  } else if (tid >= T_PF && tid < T_PF + 12) {
    tm_prefetch(&m.x + (tid - T_PF));
  } else if (tid == T_INIT) {
#pragma unroll
    for (int i = 0; i < 4; i++) mbar_init(bars + 8 * (B_EMPTY1 + i), 8);
#pragma unroll
    for (int i = 0; i < 8; i++) mbar_init(bars + 8 * (B_FULL2 + i), 1);
#pragma unroll
    for (int i = 0; i < 4; i++) mbar_init(bars + 8 * (B_EMPTY2 + i), 8);
#pragma unroll
    for (int i = 0; i < 4; i++) mbar_init(bars + 8 * (B_U + i), 1);
    mbar_init(bars + 8 * B_HA, 4);
    mbar_init(bars + 8 * B_GATE, 4);
    mbar_init(bars + 8 * B_HB, 1);
    mbar_init(bars + 8 * B_KVD, 4);
    mbar_init(bars + 8 * B_QF, 1);
    mbar_init(bars + 8 * B_ATTN, 8);
    mbar_init(bars + 8 * B_P1, 8);
    mbar_init(bars + 8 * B_C34, 1);
#pragma unroll
    for (int i = 0; i < 5; i++) mbar_init(bars + 8 * (B_YST + i), 4);
#pragma unroll
    for (int i = 0; i < 5; i++) mbar_init(bars + 8 * (B_US + i), 4);
    mbar_init(bars + 8 * B_YSIG, 1);
    mbar_init(bars + 8 * B_YFULL, 1);
    mbar_init(bars + 8 * B_EPOCH, 1);
    mbar_init(bars + 8 * B_PREP, 4);
    mbar_init(bars + 8 * B_USIG, 1);
    mbar_init(bars + 8 * B_WST, 1);
#pragma unroll
    for (int i = 3; i < 5; i++) mbar_init(bars + 8 * (B_KV + i), 1);
    mbar_init(bars + 8 * B_E3, 8);
    mbar_init(bars + 8 * B_LAST, 1);
    mbar_init(bars + 8 * B_OSIG, 1);
    mbar_init(bars + 8 * B_WOP, 1);
    fence_async_smem();
  }
  const int warp = __shfl_sync(0xffffffffu, tid >> 5, 0), wg = warp >> 2, w = warp & 3;
  __syncthreads();

  if (wg == 3) {
    asm volatile("setmaxnreg.dec.sync.aligned.u32 56;");
    if (w == 0) {
      if (lane == 0) {
#pragma unroll 1
        for (int kb = 1 + PRE2; kb < 10; kb++) {
          if (kb >= 4) mbar_wait(bars + 8 * (kb == 7 ? B_E3 : B_EMPTY1 + (kb & 3)), (kb >> 3) & 1);
          TSIF(kb >= 4, 44 + kb);
          load_stage(sb, kb, b, m);
          TSIF(kb == 3, 60);
          if (kb == TRIG_KB) mbar_arrive(bars + 8 * B_LAST);
        }
        mbar_wait(bars + 8 * B_WOP, 0);
        mbar_wait(bars + 8 * WL_TRIG, 0);
        mbar_wait(bars + 8 * B_EPOCH, 0);
        flag_wait(g_cnt + C_W + 32 * hg, (lds32(sb + OFF_EPOCH) + 1) * 16);
        TS(30);
#pragma unroll 1
        for (int j = 0; j < 8; j++) {
          if (j >= 6) mbar_wait(bars + 8 * (B_EMPTY2 + j - 6), 0);
          if (j == 4) mbar_wait(bars + 8 * B_ATTN, 0);
          TSIF(j >= 6, 100 + j);
          if (RF_GATE && j == 6) mbar_wait(bars + 8 * B_YSIG, 0);
          mbar_expect_tx(bars + 8 * (B_FULL2 + j), j == 0 ? WO_BYTES : j == 5 ? O_BYTES + WO_BYTES + 512 : O_BYTES + WO_BYTES);
          bulk_load(sb + off_w(j), g_WO + (hg * 8 + step_src(hg, j)) * 800, WO_BYTES, bars + 8 * (B_FULL2 + j));
        }
        mbar_wait(bars + 8 * (B_EMPTY2 + 3), 0);
        mbar_expect_tx(bars + 8 * B_QF, O_BYTES);
        tma_2d(sb + OFF_QS, &m.qm, 80 * hg, 128 * r, bars + 8 * B_QF);
        tma_2d(sb + OFF_QT, &m.qt, 80 * hg + 64, 128 * r, bars + 8 * B_QF);
      }
    } else if (w == 1) {
      unsigned epoch = 0;
      if (lane == 0) {
        epoch = atomicAdd(g_cnt + C_LAUNCH, 1u) / NCTA;
        asm volatile("st.shared.u32 [%0], %1;" ::"r"(sb + OFF_EPOCH), "r"(epoch) : "memory");
        mbar_arrive(bars + 8 * B_EPOCH);
        mbar_wait(bars + 8 * B_KVD, 0);
        mbar_expect_tx(bars + 8 * B_HB, 5 * 4096);
#pragma unroll 1
        for (int c = 0; c < 5; c++) {
          if (c == 3) mbar_wait(bars + 8 * B_S3, 0);
          bulk_load(sb + off_ch(c) + U_BYTES, p.ssm_k + (5 * b + c) * SEQ, 4096, bars + 8 * B_HB);
        }
#pragma unroll
        for (int c = 0; c < 4; c++) mbar_expect_tx(bars + 8 * (B_U + c), c < 3 ? U_BYTES : 2 * U_BYTES);
        const uint4* usrc = g_U + 5 * b * U_PITCH;
        mbar_wait(bars + 8 * B_USIG, 0);
        flag_wait(g_cnt + C_PREP + 32 * (b & 15), (epoch + 1) * NCTA);
        TS(23);
#pragma unroll
        for (int c = 0; c < 5; c++) {
          if (c == 3) mbar_wait(bars + 8 * (B_U + 2), 0);
          bulk_load(sb + off_ch(c), usrc + c * U_PITCH, U_BYTES, bars + 8 * (B_U + (c < 3 ? c : 3)));
          TSIF(c == 0 || c == 4, 116 + (c >> 2));
        }
      }
      epoch = __shfl_sync(0xffffffffu, epoch, 0);
      if (lane < 8) {
        const int src = (b & ~7) | step_src(hg, lane);
        mbar_wait(bars + 8 * B_OSIG, 0);
        TS(20);
        flag_wait(g_cnt + C_O + 32 * src, epoch + 1);
        if (lane >= 1 && lane < 4) bulk_load(sb + off_o(lane), g_O + src * 1280, O_BYTES, bars + 8 * (B_FULL2 + lane));
        __syncwarp(0xff);
        TS(21);
        if (lane == 5) bulk_load(sb + OFF_GATE, g_gate + 128 * r, 512, bars + 8 * (B_FULL2 + 5));
#pragma unroll 1
        for (int j = 4; j < 8; j++) {
          if (lane == j) {
            mbar_wait(bars + 8 * (j < 6 ? B_C34 : B_EMPTY2 + j - 6), 0);
            if (RF_GATE && j == 6) mbar_wait(bars + 8 * B_YSIG, 0);
            bulk_load(sb + off_o(j), g_O + src * 1280, O_BYTES, bars + 8 * (B_FULL2 + j));
          }
          __syncwarp(0xff);
        }
        TS(22);
      }
    } else if (w == 2) {
      mbar_wait(bars + 8 * B_PREP, 0);
      flag_signal(g_cnt + C_PREP, 16, lane);
      TS(25);
      if (lane == 0) mbar_arrive(bars + 8 * B_USIG);
      mbar_wait(bars + 8 * B_GATE, 0);
      if ((NOMB & 1) && lane == 0) asm volatile("fence.release.gpu;" ::: "memory");
      mbar_wait(bars + 8 * B_ATTN, 0);
      if (lane == 0) {
        if (O_DEFER) mbar_wait(bars + 8 * (B_U + 3), 0);
        asm volatile("cp.async.bulk.global.shared::cta.bulk_group [%0], [%1], 20480;\ncp.async.bulk.commit_group;\n"
                     "cp.async.bulk.wait_group 0;\nfence.proxy.async.global;" ::"l"(g_O + b * 1280), "r"(sb + OFF_OA) : "memory");
      }
      TS(74);
      if (!(NOMB & 1)) flag_signal(g_cnt + C_O + 32 * b, 1, lane);
      else if (lane == 0) flag_bump(g_cnt + C_O + 32 * b);
      TS(26);
      if (lane == 0) mbar_arrive(bars + 8 * B_OSIG);

    } else {
      if (lane == 0) {
        uint4* dst = g_WO + (hg * 8 + (r >> 1)) * 800 + (r & 1) * 80;
        mbar_wait(bars + 8 * B_P1, 0);
        mbar_wait(bars + 8 * WB_TRIG, 0);
        mbar_expect_tx(bars + 8 * B_WST, WO_BYTES / 2);
        tma_3d(sb + OFF_WS, &m.wo, 0, 40 * r, 5 * hg, bars + 8 * B_WST);
        mbar_wait(bars + 8 * B_WST, 0);
        mbar_wait(bars + 8 * WO_TRIG, 0);
#pragma unroll 1
        for (int n = 0; n < 5; n++)
          asm volatile("cp.async.bulk.global.shared::cta.bulk_group [%0], [%1], 1280;" ::"l"(dst + 160 * n), "r"(sb + OFF_WS + 1280 * n) : "memory");
        asm volatile("cp.async.bulk.commit_group;\ncp.async.bulk.wait_group 0;\nfence.proxy.async.global;" ::: "memory");
        if (!(NOMB & 4)) asm volatile("fence.release.gpu;" ::: "memory");
        flag_bump(g_cnt + C_W + 32 * hg);
        mbar_arrive(bars + 8 * B_WOP);
        TS(71);
#pragma unroll 1
        for (int c = 0; c < 5; c++) {
          mbar_wait(bars + 8 * (B_YST + c), 0);
          asm volatile("cp.async.bulk.global.shared::cta.bulk_group [%0], [%1], 4096;\ncp.async.bulk.commit_group;"
                       ::"l"(g_Y + (5 * b + c) * Y_PITCH), "r"(sb + off_ch(c)) : "memory");
          if (c == 2) {
            asm volatile("cp.async.bulk.wait_group.read 0;" ::: "memory");
            mbar_arrive(bars + 8 * B_C34);
          }
        }
        asm volatile("cp.async.bulk.wait_group 0;\nfence.proxy.async.global;" ::: "memory");
        TS(75);
        if (!(NOMB & 2)) asm volatile("fence.release.gpu;" ::: "memory");
        flag_bump(g_cnt + C_Y + 32 * (b >> 4));
        TS(27);
        mbar_arrive(bars + 8 * B_YSIG);
        mbar_expect_tx(bars + 8 * B_YFULL, 20480);
        flag_wait(g_cnt + C_Y + 32 * hg, (lds32(sb + OFF_EPOCH) + 1) * 16);
        TS(24);
        tma_2d(sb + OFF_YT, &m.y, 128 * r, 80 * hg, bars + 8 * B_YFULL);
        tma_2d(sb + OFF_YT + 10240, &m.y, 128 * r + 64, 80 * hg, bars + 8 * B_YFULL);
      }
    }
  } else {
    asm volatile("setmaxnreg.inc.sync.aligned.u32 152;");
    if (wg < 2) {
      float acc[120];
#pragma unroll
      for (int i = 0; i < 120; i++) acc[i] = 0.f;
      const uint32_t da = desc_lo(sb + wg * 8192, 16), db = desc_lo(sb + ST_W, 8192 / WS), dc = desc_lo(sb + ST_WT, 2048 / WS);
      if (PW1) pin<120>(acc);
      constexpr uint32_t B_FIRST = SUB0 && WS > 1 ? sub_bar(0) : B_FULL1;
      if (PW1 == 2) mbar_wait(bars + 8 * B_FIRST, 0);
#pragma unroll 1
      for (int kb = 0; kb < 10; kb++) {
        const uint32_t fb = bars + 8 * (B_FULL1 + (kb & 3)), so = (kb & 3) * (STAGE_BYTES >> 4);
        mbar_wait(kb ? fb : bars + 8 * B_FIRST, (kb >> 2) & 1);
        wg_fence();
#pragma unroll
        for (int k = 0; k < 4; k++) {
          constexpr int KP = 4 / WS;
          const int h = k / KP, kk = k % KP;
          if (SUB0 && k && kk == 0) mbar_wait(kb || h == WS - 1 ? fb : bars + 8 * sub_bar(h), (kb >> 2) & 1);
          WgSST<192>::mma<HI_SW128, HI_SW128>(acc, da + so + 2 * k, db + so + 128 * kk + 1536 / WS * h, 1);
          WgSST<48>::mma<HI_SW128, HI_SW32>(acc + 96, da + so + 2 * k, dc + so + 32 * kk + 384 / WS * h, 1);
        }
        wg_commit();
        wg_wait<1>();
        if (kb > 0 && lane == 0) mbar_arrive(bars + 8 * (kb == 4 ? B_E3 : B_EMPTY1 + ((kb - 1) & 3)));
      }
      mbar_wait(bars + 8 * B_EPOCH, 0);
      const uint32_t tag = lds32(sb + OFF_EPOCH) + 1;
      mbar_wait(bars + 8 * B_S3, 0);
      wg_wait<0>();
      pin<120>(acc);
      if (lane == 0) mbar_arrive(bars + 8 * B_P1);
      TSM(w == 0, 3 + wg);
      attention(acc, sb, b, wg, w, lane, tag);
    } else {
      const int tw = tid & 127, chl = 64 * (b & 1) + 8 * w + (lane >> 2);
      uint4* up = g_U + chl * U_PITCH + ((4 * (b >> 1) + (lane & 3)) ^ ((b >> 2) & 1));
      uint2 sw[10];
      uint32_t dv = 0;
      if (lane < 5) dv = __ldg(reinterpret_cast<const unsigned short*>(p.ssm_D) + 5 * b + lane);
#pragma unroll
      for (int i = 0; i < 10; i++) sw[i] = ldg64(reinterpret_cast<const uint2*>(p.shift_k) + chl + 128 * (i >> 1) + 32 * (i & 1));
      uint32_t tab[12];
      fft_tables(tab, tw);
      uint4 res[10];
#pragma unroll
      for (int i = 0; i < 10; i++) res[i] = make_uint4(0, 0, 0, 0);
#pragma unroll 1
      for (int slab = 0; slab < 5; slab++) {
#pragma unroll
        for (int i = 0; i < 8; i++) res[i] = res[i + 2];
        prep_slab(res + 8, sw, sb, slab, w, lane);
        TSIF(w == 0, 99 + 4 * slab);
#pragma unroll
        for (int i = 0; i < 8; i++) sw[i] = sw[i + 2];
      }
      TSIF(w == 0, 28);
      __syncwarp();
      if (lane == 0) mbar_arrive(bars + 8 * B_KVD + ((res[8].x ^ res[9].x) & p.zero));
      mbar_wait(bars + 8 * B_KVD, 0);
      fft_tables_store(tab, sb, tw);
      mbar_wait(bars + 8 * B_LAST, 0);
#pragma unroll
      for (int i = 0; i < 10; i++) up[(128 * (i >> 1) + 32 * (i & 1)) * U_PITCH] = res[i];
      __syncwarp();
      if (lane == 0) mbar_arrive(bars + 8 * B_PREP);
      TSIF(w == 0 && !U_TMA, 5);
      mbar_wait(bars + 8 * (G_AFTER ? B_USIG : B_LAST), 0);
      prep_gate(p, b, w, lane);
      __syncwarp();
      if (lane == 0) mbar_arrive(bars + 8 * B_GATE);
      TSIF(w == 0, 72);
      mbar_wait(bars + 8 * B_HB, 0);
      TSIF(w == 0, 123);
      const uint32_t ha = sb + U_BYTES + ((tw >> 3) * 16 + 8 + (tw & 7)) * 16;
      uint4 hv[5];
#pragma unroll
      for (int c = 0; c < 5; c++) hv[c] = lds128(ha + off_ch(c));
      __syncwarp();
#pragma unroll
      for (int c = 0; c < 5; c++) sts128((ha ^ 16) + off_ch(c), hv[c].x, hv[c].y, hv[c].z, hv[c].w);
      if (tw < 5) asm volatile("st.shared.f32 [%0], %1;" ::"r"(sb + OFF_D + 4 * tw), "f"(bf_lo(dv) * 0.125f) : "memory");
      fence_async_smem();
      __syncwarp();
      if (lane == 0) mbar_arrive(bars + 8 * B_HA);
      TSIF(w == 0, 6);
    }

    FftConst fc;
    fft_twiddles(fc, w, lane);
    mbar_wait(bars + 8 * B_HA, 0);
    fft_matrices(fc, sb, w, lane);
    if (ATT_GATE && !H_EARLY) mbar_wait(bars + 8 * B_ATTN, 0);
    TSIF(w == 0 && wg == 2, 124);
#pragma unroll 1
    for (int c = wg == 2 ? 0 : wg + 1; c < 5; c += !CH_W2 ? 3 : wg < 2 ? 5 : c ? 1 : 3) {
      conv_channel(fc, sb, c, wg, w, lane);
      if (lane == 0) mbar_arrive(bars + 8 * (B_YST + c));
      TSM(w == 0, 10 + c);
    }

    if (wg < 2) {
      const int g = lane >> 2;
      float acc[40];
#pragma unroll
      for (int i = 0; i < 40; i++) acc[i] = 0.f;
      const uint32_t da = desc_lo(sb + wg * 1024, 2048), db = desc_lo(sb, 2560);
      mbar_wait(bars + 8 * B_ATTN, 0);
      mbar_wait(bars + 8 * (B_YST + 3), 0);
      mbar_wait(bars + 8 * (B_YST + 4), 0);
      if (PW2) mbar_wait(bars + 8 * B_FULL2, 0);
#pragma unroll 1
      for (int j = 0; j < 8; j++) {
        mbar_wait(bars + 8 * (B_FULL2 + j), 0);
        const uint32_t oa = da + (off_o(j) >> 4), ob = db + (off_w(j) >> 4);
        wg_fence();
#pragma unroll
        for (int k = 0; k < 5; k++) WgSST<80>::mma<HI_NONE, HI_SW32>(acc, oa + 256 * k, ob + 32 * k, 1);
        wg_commit();
        wg_wait<1>();
        if (j >= 1 && j <= 4 && lane == 0) mbar_arrive(bars + 8 * (B_EMPTY2 + j - 1));
      }
      TSIF(w == 0 && wg == 0, 113);
      const int tr = 64 * wg + 16 * w + (lane & 15);
      const uint32_t fm = sb + OFF_QS + tr * 128, fx = (lane >> 4) ^ (tr & 7);
      const uint32_t ft = sb + OFF_QT + tr * 32 + (((lane >> 4) ^ (tr >> 2)) & 1) * 16;
      const float g0 = __uint_as_float(lds32(sb + OFF_GATE + (64 * wg + 16 * w + g) * 4));
      const float g1 = __uint_as_float(lds32(sb + OFF_GATE + (64 * wg + 16 * w + 8 + g) * 4));
      const uint32_t ga = pack2(g0, g0), gb = pack2(g1, g1);
      const uint32_t na = pack2(1.f - g0, 1.f - g0), nb = pack2(1.f - g1, 1.f - g1);

      wg_wait<0>();
      pin<40>(acc);
      TSM(w == 0, 17 + wg);
      uint32_t pb[20];
#pragma unroll
      for (int j = 0; j < 10; j++) {
        pb[2 * j] = bmul(na, pack2(acc[4 * j], acc[4 * j + 1]));
        pb[2 * j + 1] = bmul(nb, pack2(acc[4 * j + 2], acc[4 * j + 3]));
        asm volatile("" : "+r"(pb[2 * j]), "+r"(pb[2 * j + 1]));
      }
      const uint32_t ya = sb + OFF_YT + wg * 10240 + ((lane >> 4) * 8 + (lane & 7)) * 128 +
                          (((2 * w + (((lane >> 3) & 1) ^ wg)) ^ (lane & 7)) << 4);
      uint32_t qf[20];
      mbar_wait(bars + 8 * B_QF, 0);
#pragma unroll
      for (int j = 0; j < 5; j++) ldsm4(qf + 4 * j, j < 4 ? fm + ((fx ^ (2 * j)) << 4) : ft);
      mbar_wait(bars + 8 * B_YFULL, 0);
      TSIF(w == 0 && wg == 0, 19);
#pragma unroll
      for (int j = 0; j < 5; j++) {
        uint32_t y[4];
        ldsm4t(y, ya + 2048 * j);
#pragma unroll
        for (int i = 0; i < 4; i++) qf[4 * j + i] = badd(bmul((i & 1) ? gb : ga, bmul(qf[4 * j + i], y[i])), pb[4 * j + i]);
      }
#pragma unroll
      for (int j = 0; j < 5; j++) stsm4(j < 4 ? fm + ((fx ^ (2 * j)) << 4) : ft, qf + 4 * j);
      fence_async_smem();
      __syncwarp();
      if (lane == 0) {
        const int row = 64 * wg + 16 * w;
        asm volatile("cp.async.bulk.tensor.2d.global.shared::cta.bulk_group [%0, {%2, %3}], [%1];"
                     ::"l"(&m.om), "r"(sb + OFF_QS + row * 128), "r"(80 * hg), "r"(128 * r + row) : "memory");
        asm volatile("cp.async.bulk.tensor.2d.global.shared::cta.bulk_group [%0, {%2, %3}], [%1];"
                     ::"l"(&m.ot), "r"(sb + OFF_QT + row * 32), "r"(80 * hg + 64), "r"(128 * r + row) : "memory");
        asm volatile("cp.async.bulk.commit_group;\ncp.async.bulk.wait_group.read 0;" ::: "memory");
      }
      TSM(true, 40 + 4 * wg + w);
      if (ENDBAR) asm volatile("bar.sync 15, 256;" ::: "memory");
    }
  }
}

typedef CUresult (*EncodeFn)(CUtensorMap*, CUtensorMapDataType, cuuint32_t, void*, const cuuint64_t*, const cuuint64_t*,
                             const cuuint32_t*, const cuuint32_t*, CUtensorMapInterleave, CUtensorMapSwizzle,
                             CUtensorMapL2promotion, CUtensorMapFloatOOBfill);

void encode(EncodeFn fn, CUtensorMap* tm, const void* base, int rank, const cuuint64_t* dims, const cuuint64_t* strides,
            const cuuint32_t* box, CUtensorMapSwizzle swz) {
  const cuuint32_t ones[3] = {1, 1, 1};
  fn(tm, CU_TENSOR_MAP_DATA_TYPE_BFLOAT16, rank, const_cast<void*>(base), dims, strides, box, ones,
     CU_TENSOR_MAP_INTERLEAVE_NONE, swz, CU_TENSOR_MAP_L2_PROMOTION_L2_128B, CU_TENSOR_MAP_FLOAT_OOB_FILL_NONE);
}

}

extern "C" void kernel_launch(void* const* d_in, const int* in_sizes, int n_in, void* d_out, int out_size) {
  (void)in_sizes; (void)n_in; (void)out_size;
  Params p;
  p.q = (const __nv_bfloat16*)d_in[0];
  p.k = (const __nv_bfloat16*)d_in[1];
  p.v = (const __nv_bfloat16*)d_in[2];
  p.shift_k = (const __nv_bfloat16*)d_in[3];
  p.ssm_k = (const __nv_bfloat16*)d_in[4];
  p.ssm_D = (const __nv_bfloat16*)d_in[5];
  p.wqkv = (const __nv_bfloat16*)d_in[7];
  p.wo = (const __nv_bfloat16*)d_in[8];
  p.gate_w = (const __nv_bfloat16*)d_in[9];
  p.out = (__nv_bfloat16*)d_out;
  p.zero = 0;

  static EncodeFn fn = nullptr;
  static void *yaddr = nullptr, *uaddr = nullptr;
  if (!fn) {
    cudaDriverEntryPointQueryResult qr;
    void* f = nullptr;
    cudaGetDriverEntryPoint("cuTensorMapEncodeTiled", &f, cudaEnableDefault, &qr);
    fn = (EncodeFn)f;
    cudaGetSymbolAddress(&yaddr, g_Y);
    cudaGetSymbolAddress(&uaddr, g_U);
    cudaFuncSetAttribute(fused_kernel, cudaFuncAttributeMaxDynamicSharedMemorySize, SMEM_BYTES);
  }
  Maps m;
  {
    const cuuint64_t dims[3] = {640, 1024, 2}, st[2] = {2560, 1280};
    const cuuint32_t box[3] = {64, 64, 2};
    encode(fn, &m.x, p.q, 3, dims, st, box, CU_TENSOR_MAP_SWIZZLE_128B);
  }
  {
    const cuuint64_t dims[3] = {640, 640, 3}, st[2] = {3840, 1280};
    const cuuint32_t box[3] = {64, 64 / WS, 3}, boxt[3] = {16, 64 / WS, 3};
    encode(fn, &m.wm, p.wqkv, 3, dims, st, box, CU_TENSOR_MAP_SWIZZLE_128B);
    encode(fn, &m.wt, p.wqkv, 3, dims, st, boxt, CU_TENSOR_MAP_SWIZZLE_32B);
  }
  {
    const cuuint64_t dims[3] = {64, 2048, 10}, st[2] = {1280, 128};
    const cuuint32_t boxk[3] = {64, 35, 1}, boxv[3] = {64, 32, 1};
    encode(fn, &m.k, p.k, 3, dims, st, boxk, CU_TENSOR_MAP_SWIZZLE_128B);
    encode(fn, &m.v, p.v, 3, dims, st, boxv, CU_TENSOR_MAP_SWIZZLE_128B);
  }
  {
    const cuuint64_t dims[3] = {16, 640, 40}, st[2] = {1280, 32};
    const cuuint32_t box[3] = {16, 40, 5};
    encode(fn, &m.wo, p.wo, 3, dims, st, box, CU_TENSOR_MAP_SWIZZLE_32B);
  }
  {
    const cuuint64_t dims[2] = {2048, 640}, st[1] = {Y_PITCH * 16};
    const cuuint32_t box[2] = {64, 80};
    encode(fn, &m.y, yaddr, 2, dims, st, box, CU_TENSOR_MAP_SWIZZLE_128B);
    const cuuint64_t stu[1] = {U_PITCH * 16};
    const cuuint32_t boxu[2] = {32, 64};
    encode(fn, &m.u, uaddr, 2, dims, stu, boxu, CU_TENSOR_MAP_SWIZZLE_NONE);
  }
  {
    const cuuint64_t dims[2] = {640, 2048}, st[1] = {1280};
    const cuuint32_t bqm[2] = {64, 128}, bqt[2] = {16, 128}, bom[2] = {64, 16}, bot[2] = {16, 16};
    encode(fn, &m.qm, p.q, 2, dims, st, bqm, CU_TENSOR_MAP_SWIZZLE_128B);
    encode(fn, &m.qt, p.q, 2, dims, st, bqt, CU_TENSOR_MAP_SWIZZLE_32B);
    encode(fn, &m.om, p.out, 2, dims, st, bom, CU_TENSOR_MAP_SWIZZLE_128B);
    encode(fn, &m.ot, p.out, 2, dims, st, bot, CU_TENSOR_MAP_SWIZZLE_32B);
  }
  fused_kernel<<<NCTA, NTHR, SMEM_BYTES>>>(m, p);
}
```

```cpp
#include <cuda.h>
#include <cuda_bf16.h>
#include <cuda_runtime.h>
#include <stdint.h>

namespace {

constexpr int SEQ = 2048, DIM = 640, NCTA = 128, NTHR = 512;

#define TRIG_KB 9
#define KV_KB 2
#define DEV_EXIT 0
#define ATT_GATE 1
#define G_AFTER 0
#define FENCE_LO 0
#define FENCE_HI 0
#define PW1 2
#define PW2 1
#define ENDBAR 0
#define PAD_KB 0
#define Y_ALIAS 1
#define H_EARLY 1
#define NOMB 0
#define SRC_ROT 0
#define WAIT_NS 0
#define WB_TRIG B_USIG
#define G_POS 0
#define TAILF 1
#define T_ISSUE 384
#define T_PF 416
#define T_INIT 448
#define ATT_MERGE 0
#define BMAP 1
#define PRE2 1
#define KV_MIX 0
#define O_DEFER 0
#define CH_W2 0
#define HALO_FIRST 1
#define PREV_EARLY 0
#define TLBW 0
#define TLB_TRIG B_FULL1
#define ACQ 0
#define U_TMA 0
#define U_GATE 0
#define RF_GATE 0
#define WO_TRIG B_WST
#define WL_TRIG B_WOP
#define WO_GATE 1

constexpr uint32_t STAGE_BYTES = 47104, ST_W = 16384, ST_WT = 40960;
constexpr uint32_t O_BYTES = 20480, WO_BYTES = 12800;
constexpr uint32_t OFF_OA = 0;
constexpr uint32_t OFF_QS = 3 * O_BYTES, OFF_QT = OFF_QS + 16384;
constexpr uint32_t OFF_WC = 81920;
constexpr uint32_t OFF_WA = 94720;
constexpr uint32_t OFF_GATE = 145920;
constexpr uint32_t OFF_KVX = 147968;
constexpr uint32_t OFF_D = OFF_GATE + 512;
constexpr uint32_t OFF_CH3 = 163840;
constexpr uint32_t CH_BYTES = 12288, U_BYTES = 4096;
constexpr uint32_t OFF_FT = 225280, OFF_GT = 229376;
constexpr uint32_t OFF_CH0 = 188416;
constexpr uint32_t OFF_KVS = OFF_CH0, KVS_V = 4480, KVS_BYTES = 8576;
constexpr uint32_t OFF_WS = OFF_WA;
__device__ __forceinline__ uint32_t off_us(int s) { return OFF_CH0 + 4096 * ((0x65320 >> (4 * s)) & 7); }
constexpr uint32_t OFF_YT = 163840;
constexpr uint32_t OFF_BAR = 231936;
constexpr uint32_t SMEM_BYTES = OFF_BAR + 512;

enum : uint32_t {
  B_FULL1 = 0, B_EMPTY1 = 4, B_S3 = 7, B_FULL2 = 52, B_EMPTY2 = 13, B_U = 8, B_GATE = 12, B_HA = 19, B_HB = 20,
  B_ATTN = 21, B_C34 = 22, B_CONV = 23, B_YFULL = 24, B_EPOCH = 25, B_PREP = 26, B_P1 = 27, B_LAST = 28,
  B_E3 = 29, B_OSIG = 30, B_WOP = 31, B_USIG = 32, B_WST = 33, B_KV = 34, B_KVD = 39, B_HC = 61, B_QF = 62, B_YST = 40,
  B_US = 45, B_YSIG = 50
};
constexpr uint32_t OFF_EPOCH = OFF_BAR + 8 * 51;
__device__ __forceinline__ uint32_t off_o(int j) { return j < 4 ? OFF_OA + j * O_BYTES : j < 6 ? OFF_CH0 + (j - 4) * O_BYTES : OFF_OA + (j - 6) * O_BYTES; }
__device__ __forceinline__ uint32_t off_w(int j) { return j < 4 ? OFF_WA + j * WO_BYTES : j == 4 ? OFF_KVX : j == 5 ? OFF_WC : OFF_WA + (j - 6) * WO_BYTES; }
__device__ __forceinline__ int step_src(int hg, int j) { return SRC_ROT ? (hg + j) & 7 : j == 0 ? hg : j <= hg ? j - 1 : j; }
__device__ __forceinline__ bool tail_first(int hg) { return TAILF && (hg & 3) == 3; }
__device__ __forceinline__ uint32_t off_ch(int c) { return (c < 3 ? OFF_CH0 : OFF_CH3 - 3 * CH_BYTES) + c * CH_BYTES; }

#define U_PITCH 264
__device__ __align__(1024) uint4 g_U[DIM * U_PITCH];
__device__ uint4 g_O[NCTA * 1280];
#define g_Y g_U
constexpr int Y_PITCH = U_PITCH;
__device__ uint4 g_WO[64 * 800];
__device__ uint4 g_halo[NCTA * 2 * 7 * 32];
__device__ float g_gate[SEQ + PAD_KB * 256];
__device__ unsigned g_cnt[32 * (1 + 2 * 16 + 8 + NCTA)];
constexpr int C_LAUNCH = 0, C_PREP = 32, C_Y = 32 * 17, C_W = 32 * 33, C_O = 32 * 41;

#define TSM(cond, slot) do { } while (0)
#define TSIF(cond, slot) do { if (__LINE__ >= FENCE_LO && __LINE__ < FENCE_HI) sched_fence(); } while (0)
__device__ __forceinline__ void sched_fence() {
  asm volatile("{\n.reg .pred p;\n.reg .u32 c;\nmov.u32 c, %%clock;\nsetp.eq.u32 p, c, 0;\n@p st.shared.u32 [%0], c;\n}"
               ::"r"(1024 + OFF_EPOCH + 4) : "memory");
}
#define TS(slot) TSIF(true, slot)

struct Params {
  const __nv_bfloat16 *q, *k, *v, *shift_k, *ssm_k, *ssm_D, *wqkv, *wo, *gate_w;
  __nv_bfloat16* out;
  uint32_t zero;
};

#define POLL_NS 0
constexpr int SPIN_LIMIT = 1 << 17;

__device__ __forceinline__ void mbar_init(uint32_t bar, uint32_t count) {
  asm volatile("mbarrier.init.shared::cta.b64 [%0], %1;" ::"r"(bar), "r"(count) : "memory");
}
__device__ __forceinline__ void mbar_expect_tx(uint32_t bar, uint32_t bytes) {
  asm volatile("mbarrier.arrive.expect_tx.shared::cta.b64 _, [%0], %1;" ::"r"(bar), "r"(bytes) : "memory");
}
__device__ __forceinline__ void mbar_arrive(uint32_t bar) {
  asm volatile("mbarrier.arrive.shared::cta.b64 _, [%0];" ::"r"(bar) : "memory");
}
__device__ __forceinline__ void mbar_wait(uint32_t bar, uint32_t parity) {
  uint32_t ok;
  int spins = 0;
  do {
    if (WAIT_NS)
      asm volatile("{\n.reg .pred p;\nmbarrier.try_wait.parity.shared::cta.b64 p, [%1], %2, %3;\nselp.b32 %0, 1, 0, p;\n}"
                   : "=r"(ok) : "r"(bar), "r"(parity), "r"(WAIT_NS) : "memory");
    else
      asm volatile("{\n.reg .pred p;\nmbarrier.try_wait.parity.shared::cta.b64 p, [%1], %2;\nselp.b32 %0, 1, 0, p;\n}"
                   : "=r"(ok) : "r"(bar), "r"(parity) : "memory");
    if (++spins > SPIN_LIMIT) break;
  } while (!ok);
}
__device__ __forceinline__ void flag_poll(const unsigned* p, unsigned target) {
  unsigned v;
  int spins = 0;
  do {
    if (POLL_NS && spins) __nanosleep(POLL_NS);
    asm volatile("ld.relaxed.gpu.global.u32 %0, [%1];" : "=r"(v) : "l"(p) : "memory");
    if (++spins > SPIN_LIMIT) break;
  } while ((int)(v - target) < 0);
}
__device__ __forceinline__ void flag_wait(const unsigned* p, unsigned target) {
  flag_poll(p, target);
  if (ACQ) asm volatile("fence.acquire.gpu;\nfence.proxy.async.global;" ::: "memory");
}
__device__ __forceinline__ void flag_signal(unsigned* p, int n, int lane) {
  if (lane == 0) asm volatile("fence.release.gpu;" ::: "memory");
  __syncwarp();
  if (lane < n) asm volatile("red.relaxed.gpu.global.add.u32 [%0], 1;" ::"l"(p + 32 * lane) : "memory");
}
__device__ __forceinline__ void flag_bump(unsigned* p) {
  asm volatile("red.relaxed.gpu.global.add.u32 [%0], 1;" ::"l"(p) : "memory");
}
__device__ __forceinline__ void fence_async_smem() { asm volatile("fence.proxy.async.shared::cta;" ::: "memory"); }
__device__ __forceinline__ void wg_sync(int id) { asm volatile("bar.sync %0, 128;" ::"r"(id) : "memory"); }

__device__ __forceinline__ void tma_2d(uint32_t dst, const CUtensorMap* tm, int c0, int c1, uint32_t bar) {
  asm volatile("cp.async.bulk.tensor.2d.shared::cluster.global.mbarrier::complete_tx::bytes [%0], [%1, {%3, %4}], [%2];"
               ::"r"(dst), "l"(tm), "r"(bar), "r"(c0), "r"(c1) : "memory");
}
__device__ __forceinline__ void tma_3d(uint32_t dst, const CUtensorMap* tm, int c0, int c1, int c2, uint32_t bar) {
  asm volatile("cp.async.bulk.tensor.3d.shared::cluster.global.mbarrier::complete_tx::bytes [%0], [%1, {%3, %4, %5}], [%2];"
               ::"r"(dst), "l"(tm), "r"(bar), "r"(c0), "r"(c1), "r"(c2) : "memory");
}
__device__ __forceinline__ void bulk_load(uint32_t dst, const void* src, uint32_t bytes, uint32_t bar) {
  asm volatile("cp.async.bulk.shared::cluster.global.mbarrier::complete_tx::bytes [%0], [%1], %2, [%3];"
               ::"r"(dst), "l"(src), "r"(bytes), "r"(bar) : "memory");
}
__device__ __forceinline__ void tm_prefetch(const CUtensorMap* tm) {
  asm volatile("prefetch.tensormap [%0];" ::"l"(tm) : "memory");
}

__device__ __forceinline__ void wg_fence() { asm volatile("wgmma.fence.sync.aligned;" ::: "memory"); }
__device__ __forceinline__ void wg_commit() { asm volatile("wgmma.commit_group.sync.aligned;" ::: "memory"); }
template <int N> __device__ __forceinline__ void wg_wait() { asm volatile("wgmma.wait_group.sync.aligned %0;" ::"n"(N) : "memory"); }
__device__ __forceinline__ uint32_t desc_lo(uint32_t addr, uint32_t lbo) { return ((addr & 0x3FFFF) >> 4) | ((lbo >> 4) << 16); }
constexpr uint32_t desc_hi(uint32_t sbo, uint32_t swz) { return (sbo >> 4) | (swz << 30); }
constexpr uint32_t HI_SW128 = desc_hi(1024, 1), HI_SW64 = desc_hi(512, 2), HI_SW32 = desc_hi(256, 3), HI_NONE = desc_hi(128, 0);
template <int N> __device__ __forceinline__ void pin(float* d) {
#pragma unroll
  for (int i = 0; i < N; i++) asm volatile("" : "+f"(d[i])::"memory");
}

__device__ __forceinline__ uint32_t lds32(uint32_t a) {
  uint32_t v;
  asm volatile("ld.volatile.shared.u32 %0, [%1];" : "=r"(v) : "r"(a) : "memory");
  return v;
}
__device__ __forceinline__ uint4 ldg128(const void* a) {
  uint4 v;
  asm volatile("ld.global.nc.v4.u32 {%0, %1, %2, %3}, [%4];" : "=r"(v.x), "=r"(v.y), "=r"(v.z), "=r"(v.w) : "l"(a) : "memory");
  return v;
}
__device__ __forceinline__ uint2 ldg64(const void* a) {
  uint2 v;
  asm volatile("ld.global.nc.v2.u32 {%0, %1}, [%2];" : "=r"(v.x), "=r"(v.y) : "l"(a) : "memory");
  return v;
}
__device__ __forceinline__ void ldsm4(uint32_t* r, uint32_t a) {
  asm volatile("ldmatrix.sync.aligned.m8n8.x4.shared.b16 {%0, %1, %2, %3}, [%4];"
               : "=r"(r[0]), "=r"(r[1]), "=r"(r[2]), "=r"(r[3]) : "r"(a) : "memory");
}
__device__ __forceinline__ void ldsm4t(uint32_t* r, uint32_t a) {
  asm volatile("ldmatrix.sync.aligned.m8n8.x4.trans.shared.b16 {%0, %1, %2, %3}, [%4];"
               : "=r"(r[0]), "=r"(r[1]), "=r"(r[2]), "=r"(r[3]) : "r"(a) : "memory");
}
__device__ __forceinline__ uint4 lds128(uint32_t a) {
  uint4 v;
  asm volatile("ld.shared.v4.u32 {%0, %1, %2, %3}, [%4];" : "=r"(v.x), "=r"(v.y), "=r"(v.z), "=r"(v.w) : "r"(a) : "memory");
  return v;
}
__device__ __forceinline__ void sts128(uint32_t a, uint32_t x, uint32_t y, uint32_t z, uint32_t w) {
  asm volatile("st.shared.v4.u32 [%0], {%1, %2, %3, %4};" ::"r"(a), "r"(x), "r"(y), "r"(z), "r"(w) : "memory");
}
__device__ __forceinline__ void stsm4(uint32_t a, const uint32_t* r) {
  asm volatile("stmatrix.sync.aligned.m8n8.x4.shared.b16 [%0], {%1, %2, %3, %4};" ::"r"(a), "r"(r[0]), "r"(r[1]), "r"(r[2]), "r"(r[3]) : "memory");
}
__device__ __forceinline__ void stsm4t(uint32_t a, const uint32_t* r) {
  asm volatile("stmatrix.sync.aligned.m8n8.x4.trans.shared.b16 [%0], {%1, %2, %3, %4};" ::"r"(a), "r"(r[0]), "r"(r[1]), "r"(r[2]), "r"(r[3]) : "memory");
}
__device__ __forceinline__ uint32_t pack2(float lo, float hi) {
  uint32_t r;
  asm("cvt.rn.bf16x2.f32 %0, %1, %2;" : "=r"(r) : "f"(hi), "f"(lo));
  return r;
}
__device__ __forceinline__ uint32_t movm(uint32_t a) {
  uint32_t d;
  asm volatile("movmatrix.sync.aligned.m8n8.trans.b16 %0, %1;" : "=r"(d) : "r"(a));
  return d;
}
__device__ __forceinline__ uint32_t bmul(uint32_t a, uint32_t b) {
  uint32_t d;
  asm("mul.rn.bf16x2 %0, %1, %2;" : "=r"(d) : "r"(a), "r"(b));
  return d;
}
__device__ __forceinline__ uint32_t badd(uint32_t a, uint32_t b) {
  uint32_t d;
  asm("add.rn.bf16x2 %0, %1, %2;" : "=r"(d) : "r"(a), "r"(b));
  return d;
}
__device__ __forceinline__ float bf_lo(uint32_t x) { return __uint_as_float(x << 16); }
__device__ __forceinline__ float bf_hi(uint32_t x) { return __uint_as_float(x & 0xFFFF0000u); }
__device__ __forceinline__ float ex2(float x) {
  float y;
  asm("ex2.approx.ftz.f32 %0, %1;" : "=f"(y) : "f"(x));
  return y;
}
__device__ __forceinline__ float rcp(float x) {
  float y;
  asm("rcp.approx.ftz.f32 %0, %1;" : "=f"(y) : "f"(x));
  return y;
}
__device__ __forceinline__ void mma16816(float* d, uint32_t a0, uint32_t a1, uint32_t a2, uint32_t a3, uint32_t b0, uint32_t b1) {
  asm volatile("mma.sync.aligned.m16n8k16.row.col.f32.bf16.bf16.f32 {%0, %1, %2, %3}, {%4, %5, %6, %7}, {%8, %9}, {%0, %1, %2, %3};"
               : "+f"(d[0]), "+f"(d[1]), "+f"(d[2]), "+f"(d[3])
               : "r"(a0), "r"(a1), "r"(a2), "r"(a3), "r"(b0), "r"(b1));
}
__device__ __forceinline__ void mma1688(float* d, uint32_t a0, uint32_t a1, uint32_t b0) {
  asm volatile("mma.sync.aligned.m16n8k8.row.col.f32.bf16.bf16.f32 {%0, %1, %2, %3}, {%4, %5}, {%6}, {%0, %1, %2, %3};"
               : "+f"(d[0]), "+f"(d[1]), "+f"(d[2]), "+f"(d[3])
               : "r"(a0), "r"(a1), "r"(b0));
}

template <int N> struct WgRS;
template <int N> struct WgSST;
template <> struct WgRS<32> {
  template <uint32_t HB>
  static __device__ __forceinline__ void mma(float* d, const uint32_t* a, uint32_t db) {
    asm volatile("{\n.reg .pred p;\n.reg .b64 db;\nsetp.ne.b32 p, %22, 0;\n"
      "mov.b64 db, {%20, %21};\n"
      "wgmma.mma_async.sync.aligned.m64n32k16.f32.bf16.bf16 {"
      "%0, %1, %2, %3, %4, %5, %6, %7, %8, %9, %10, %11, %12, %13, %14, %15"
      "}, {%16, %17, %18, %19}, db, p, 1, 1, 1;\n}\n"
      : "+f"(d[0]), "+f"(d[1]), "+f"(d[2]), "+f"(d[3]), "+f"(d[4]), "+f"(d[5]), "+f"(d[6]), "+f"(d[7]),
        "+f"(d[8]), "+f"(d[9]), "+f"(d[10]), "+f"(d[11]), "+f"(d[12]), "+f"(d[13]), "+f"(d[14]), "+f"(d[15])
      : "r"(a[0]), "r"(a[1]), "r"(a[2]), "r"(a[3]), "r"(db), "n"(HB), "n"(1));
  }
  template <uint32_t HB>
  static __device__ __forceinline__ void set(float* d, const uint32_t* a, uint32_t db) {
    asm volatile("{\n.reg .pred p;\n.reg .b64 db;\nsetp.ne.b32 p, %22, 0;\n"
      "mov.b64 db, {%20, %21};\n"
      "wgmma.mma_async.sync.aligned.m64n32k16.f32.bf16.bf16 {"
      "%0, %1, %2, %3, %4, %5, %6, %7, %8, %9, %10, %11, %12, %13, %14, %15"
      "}, {%16, %17, %18, %19}, db, p, 1, 1, 1;\n}\n"
      : "=f"(d[0]), "=f"(d[1]), "=f"(d[2]), "=f"(d[3]), "=f"(d[4]), "=f"(d[5]), "=f"(d[6]), "=f"(d[7]),
        "=f"(d[8]), "=f"(d[9]), "=f"(d[10]), "=f"(d[11]), "=f"(d[12]), "=f"(d[13]), "=f"(d[14]), "=f"(d[15])
      : "r"(a[0]), "r"(a[1]), "r"(a[2]), "r"(a[3]), "r"(db), "n"(HB), "n"(0));
  }
};
template <> struct WgRS<64> {
  template <uint32_t HB>
  static __device__ __forceinline__ void mma(float* d, const uint32_t* a, uint32_t db) {
    asm volatile("{\n.reg .pred p;\n.reg .b64 db;\nsetp.ne.b32 p, %38, 0;\n"
      "mov.b64 db, {%36, %37};\n"
      "wgmma.mma_async.sync.aligned.m64n64k16.f32.bf16.bf16 {"
      "%0, %1, %2, %3, %4, %5, %6, %7, %8, %9, %10, %11, %12, %13, %14, %15, "
      "%16, %17, %18, %19, %20, %21, %22, %23, %24, %25, %26, %27, %28, %29, %30, %31"
      "}, {%32, %33, %34, %35}, db, p, 1, 1, 1;\n}\n"
      : "+f"(d[0]), "+f"(d[1]), "+f"(d[2]), "+f"(d[3]), "+f"(d[4]), "+f"(d[5]), "+f"(d[6]), "+f"(d[7]),
        "+f"(d[8]), "+f"(d[9]), "+f"(d[10]), "+f"(d[11]), "+f"(d[12]), "+f"(d[13]), "+f"(d[14]), "+f"(d[15]),
        "+f"(d[16]), "+f"(d[17]), "+f"(d[18]), "+f"(d[19]), "+f"(d[20]), "+f"(d[21]), "+f"(d[22]), "+f"(d[23]),
        "+f"(d[24]), "+f"(d[25]), "+f"(d[26]), "+f"(d[27]), "+f"(d[28]), "+f"(d[29]), "+f"(d[30]), "+f"(d[31])
      : "r"(a[0]), "r"(a[1]), "r"(a[2]), "r"(a[3]), "r"(db), "n"(HB), "n"(1));
  }
  template <uint32_t HB>
  static __device__ __forceinline__ void set(float* d, const uint32_t* a, uint32_t db) {
    asm volatile("{\n.reg .pred p;\n.reg .b64 db;\nsetp.ne.b32 p, %38, 0;\n"
      "mov.b64 db, {%36, %37};\n"
      "wgmma.mma_async.sync.aligned.m64n64k16.f32.bf16.bf16 {"
      "%0, %1, %2, %3, %4, %5, %6, %7, %8, %9, %10, %11, %12, %13, %14, %15, "
      "%16, %17, %18, %19, %20, %21, %22, %23, %24, %25, %26, %27, %28, %29, %30, %31"
      "}, {%32, %33, %34, %35}, db, p, 1, 1, 1;\n}\n"
      : "=f"(d[0]), "=f"(d[1]), "=f"(d[2]), "=f"(d[3]), "=f"(d[4]), "=f"(d[5]), "=f"(d[6]), "=f"(d[7]),
        "=f"(d[8]), "=f"(d[9]), "=f"(d[10]), "=f"(d[11]), "=f"(d[12]), "=f"(d[13]), "=f"(d[14]), "=f"(d[15]),
        "=f"(d[16]), "=f"(d[17]), "=f"(d[18]), "=f"(d[19]), "=f"(d[20]), "=f"(d[21]), "=f"(d[22]), "=f"(d[23]),
        "=f"(d[24]), "=f"(d[25]), "=f"(d[26]), "=f"(d[27]), "=f"(d[28]), "=f"(d[29]), "=f"(d[30]), "=f"(d[31])
      : "r"(a[0]), "r"(a[1]), "r"(a[2]), "r"(a[3]), "r"(db), "n"(HB), "n"(0));
  }
};
template <> struct WgSST<48> {
  template <uint32_t HA, uint32_t HB>
  static __device__ __forceinline__ void mma(float* d, uint32_t da, uint32_t db, int sc) {
    asm volatile("{\n.reg .pred p;\n.reg .b64 da, db;\nsetp.ne.b32 p, %28, 0;\n"
      "mov.b64 da, {%24, %25};\nmov.b64 db, {%26, %27};\n"
      "wgmma.mma_async.sync.aligned.m64n48k16.f32.bf16.bf16 {"
      "%0, %1, %2, %3, %4, %5, %6, %7, %8, %9, %10, %11, %12, %13, %14, %15, "
      "%16, %17, %18, %19, %20, %21, %22, %23"
      "}, da, db, p, 1, 1, 0, 1;\n}\n"
      : "+f"(d[0]), "+f"(d[1]), "+f"(d[2]), "+f"(d[3]), "+f"(d[4]), "+f"(d[5]), "+f"(d[6]), "+f"(d[7]),
        "+f"(d[8]), "+f"(d[9]), "+f"(d[10]), "+f"(d[11]), "+f"(d[12]), "+f"(d[13]), "+f"(d[14]), "+f"(d[15]),
        "+f"(d[16]), "+f"(d[17]), "+f"(d[18]), "+f"(d[19]), "+f"(d[20]), "+f"(d[21]), "+f"(d[22]), "+f"(d[23])
      : "r"(da), "n"(HA), "r"(db), "n"(HB), "r"(sc));
  }
};
template <> struct WgSST<80> {
  template <uint32_t HA, uint32_t HB>
  static __device__ __forceinline__ void mma(float* d, uint32_t da, uint32_t db, int sc) {
    asm volatile("{\n.reg .pred p;\n.reg .b64 da, db;\nsetp.ne.b32 p, %44, 0;\n"
      "mov.b64 da, {%40, %41};\nmov.b64 db, {%42, %43};\n"
      "wgmma.mma_async.sync.aligned.m64n80k16.f32.bf16.bf16 {"
      "%0, %1, %2, %3, %4, %5, %6, %7, %8, %9, %10, %11, %12, %13, %14, %15, "
      "%16, %17, %18, %19, %20, %21, %22, %23, %24, %25, %26, %27, %28, %29, %30, %31, "
      "%32, %33, %34, %35, %36, %37, %38, %39"
      "}, da, db, p, 1, 1, 0, 1;\n}\n"
      : "+f"(d[0]), "+f"(d[1]), "+f"(d[2]), "+f"(d[3]), "+f"(d[4]), "+f"(d[5]), "+f"(d[6]), "+f"(d[7]),
        "+f"(d[8]), "+f"(d[9]), "+f"(d[10]), "+f"(d[11]), "+f"(d[12]), "+f"(d[13]), "+f"(d[14]), "+f"(d[15]),
        "+f"(d[16]), "+f"(d[17]), "+f"(d[18]), "+f"(d[19]), "+f"(d[20]), "+f"(d[21]), "+f"(d[22]), "+f"(d[23]),
        "+f"(d[24]), "+f"(d[25]), "+f"(d[26]), "+f"(d[27]), "+f"(d[28]), "+f"(d[29]), "+f"(d[30]), "+f"(d[31]),
        "+f"(d[32]), "+f"(d[33]), "+f"(d[34]), "+f"(d[35]), "+f"(d[36]), "+f"(d[37]), "+f"(d[38]), "+f"(d[39])
      : "r"(da), "n"(HA), "r"(db), "n"(HB), "r"(sc));
  }
};
template <> struct WgSST<192> {
  template <uint32_t HA, uint32_t HB>
  static __device__ __forceinline__ void mma(float* d, uint32_t da, uint32_t db, int sc) {
    asm volatile("{\n.reg .pred p;\n.reg .b64 da, db;\nsetp.ne.b32 p, %100, 0;\n"
      "mov.b64 da, {%96, %97};\nmov.b64 db, {%98, %99};\n"
      "wgmma.mma_async.sync.aligned.m64n192k16.f32.bf16.bf16 {"
      "%0, %1, %2, %3, %4, %5, %6, %7, %8, %9, %10, %11, %12, %13, %14, %15, "
      "%16, %17, %18, %19, %20, %21, %22, %23, %24, %25, %26, %27, %28, %29, %30, %31, "
      "%32, %33, %34, %35, %36, %37, %38, %39, %40, %41, %42, %43, %44, %45, %46, %47, "
      "%48, %49, %50, %51, %52, %53, %54, %55, %56, %57, %58, %59, %60, %61, %62, %63, "
      "%64, %65, %66, %67, %68, %69, %70, %71, %72, %73, %74, %75, %76, %77, %78, %79, "
      "%80, %81, %82, %83, %84, %85, %86, %87, %88, %89, %90, %91, %92, %93, %94, %95"
      "}, da, db, p, 1, 1, 0, 1;\n}\n"
      : "+f"(d[0]), "+f"(d[1]), "+f"(d[2]), "+f"(d[3]), "+f"(d[4]), "+f"(d[5]), "+f"(d[6]), "+f"(d[7]),
        "+f"(d[8]), "+f"(d[9]), "+f"(d[10]), "+f"(d[11]), "+f"(d[12]), "+f"(d[13]), "+f"(d[14]), "+f"(d[15]),
        "+f"(d[16]), "+f"(d[17]), "+f"(d[18]), "+f"(d[19]), "+f"(d[20]), "+f"(d[21]), "+f"(d[22]), "+f"(d[23]),
        "+f"(d[24]), "+f"(d[25]), "+f"(d[26]), "+f"(d[27]), "+f"(d[28]), "+f"(d[29]), "+f"(d[30]), "+f"(d[31]),
        "+f"(d[32]), "+f"(d[33]), "+f"(d[34]), "+f"(d[35]), "+f"(d[36]), "+f"(d[37]), "+f"(d[38]), "+f"(d[39]),
        "+f"(d[40]), "+f"(d[41]), "+f"(d[42]), "+f"(d[43]), "+f"(d[44]), "+f"(d[45]), "+f"(d[46]), "+f"(d[47]),
        "+f"(d[48]), "+f"(d[49]), "+f"(d[50]), "+f"(d[51]), "+f"(d[52]), "+f"(d[53]), "+f"(d[54]), "+f"(d[55]),
        "+f"(d[56]), "+f"(d[57]), "+f"(d[58]), "+f"(d[59]), "+f"(d[60]), "+f"(d[61]), "+f"(d[62]), "+f"(d[63]),
        "+f"(d[64]), "+f"(d[65]), "+f"(d[66]), "+f"(d[67]), "+f"(d[68]), "+f"(d[69]), "+f"(d[70]), "+f"(d[71]),
        "+f"(d[72]), "+f"(d[73]), "+f"(d[74]), "+f"(d[75]), "+f"(d[76]), "+f"(d[77]), "+f"(d[78]), "+f"(d[79]),
        "+f"(d[80]), "+f"(d[81]), "+f"(d[82]), "+f"(d[83]), "+f"(d[84]), "+f"(d[85]), "+f"(d[86]), "+f"(d[87]),
        "+f"(d[88]), "+f"(d[89]), "+f"(d[90]), "+f"(d[91]), "+f"(d[92]), "+f"(d[93]), "+f"(d[94]), "+f"(d[95])
      : "r"(da), "n"(HA), "r"(db), "n"(HB), "r"(sc));
  }
};

struct FftConst {
  uint32_t f[2][4], fi[4][4];
  float ta[4], tb[4];
};
__device__ __forceinline__ void cis(int m, float scale, float& c, float& s) {
  const float a = (float)m * (-6.283185307179586f * scale);
  c = __cosf(a);
  s = __sinf(a);
}
__device__ __forceinline__ void fft_tables(uint32_t (&v)[12], int tw) {
  const int row = tw >> 2, ch = tw & 3;
#pragma unroll
  for (int i = 0; i < 4; i++) {
    float c[2], s[2], x[2];
#pragma unroll
    for (int e = 0; e < 2; e++) {
      cis((((32 * (8 * ch + 2 * i + e) + 15) * (4 * row - 63) + 2048) & 4095) - 2048, 1.f / 4096, c[e], s[e]);
      float gc, gs;
      cis((((row & 15) * (8 * (ch & 1) + 2 * i + e) + 8) & 15) - 8, 1.f / 16, gc, gs);
      x[e] = (row >> 4) == (ch >> 1) ? gc : (ch >> 1) ? gs : -gs;
    }
    v[i] = pack2(c[0] * 0.125f, c[1] * 0.125f);
    v[4 + i] = pack2(s[0] * 0.125f, s[1] * 0.125f);
    v[8 + i] = pack2(x[0], x[1]);
  }
#pragma unroll
  for (int i = 0; i < 12; i++) asm volatile("" : "+r"(v[i]));
}
__device__ __forceinline__ void fft_tables_store(const uint32_t (&v)[12], uint32_t sb, int tw) {
  const int row = tw >> 2;
  const uint32_t x = ((tw ^ (row >> 1)) & 3) << 4, a = sb + OFF_FT + (16 * (row >> 3) + (row & 7)) * 64 + x;
  sts128(a, v[0], v[1], v[2], v[3]);
  sts128(a + 512, v[4], v[5], v[6], v[7]);
  sts128(sb + OFF_GT + row * 64 + x, v[8], v[9], v[10], v[11]);
}
__device__ __forceinline__ void fft_twiddles(FftConst& k, int w, int lane) {
#pragma unroll
  for (int i = 0; i < 4; i++) {
    float c, s;
    cis((2 * (8 * (i >> 1) + 2 * (lane & 3) + (i & 1)) - 15) * (4 * (8 * w + (lane >> 2)) - 63), 1.f / 4096, c, s);
    k.ta[i] = __fdividef(-s, 1.f + c);
    k.tb[i] = s;
  }
  pin<4>(k.ta);
  pin<4>(k.tb);
}
__device__ __forceinline__ void fft_matrices(FftConst& k, uint32_t sb, int w, int lane) {
  const uint32_t x = (lane >> 1) & 3;
#pragma unroll
  for (int i = 0; i < 2; i++) {
    ldsm4(k.f[i], sb + OFF_FT + (16 * w + (lane & 15)) * 64 + (((2 * i + (lane >> 4)) ^ x) << 4));
    ldsm4t(k.fi[i], sb + OFF_FT + (32 * i + lane) * 64 + ((w ^ x) << 4));
#pragma unroll
    for (int j = 0; j < 4; j++) {
      k.fi[2 + i][j] = (j & 1) ? k.fi[i][j - 1] ^ 0x80008000u : k.fi[i][j + 1];
      asm volatile("" : "+r"(k.fi[2 + i][j]));
    }
  }
}
template <bool INV> __device__ __forceinline__ void rot(float& x, float& y, float a, float b) {
  x = fmaf(INV ? -a : a, y, x);
  y = fmaf(INV ? -b : b, x, y);
  x = fmaf(INV ? -a : a, y, x);
}
__device__ __forceinline__ void twiddle_fwd(uint32_t (&a)[4][4], float* d, const FftConst& k) {
#pragma unroll
  for (int q = 0; q < 4; q++)
#pragma unroll
    for (int j = 0; j < 2; j++) {
      float* x = d + 8 * q + 4 * j;
      rot<false>(x[0], x[2], k.ta[2 * j], k.tb[2 * j]);
      rot<false>(x[1], x[3], k.ta[2 * j + 1], k.tb[2 * j + 1]);
      a[q & 2][2 * j + (q & 1)] = pack2(x[0], x[1]);
      a[(q & 2) + 1][2 * j + (q & 1)] = pack2(x[2], x[3]);
    }
}
__device__ __forceinline__ void g_step(float* d, const uint32_t (&a)[4][4], uint32_t dre, uint32_t dim) {
  WgRS<32>::set<HI_SW64>(d, a[0], dre);
  WgRS<32>::set<HI_SW64>(d + 16, a[2], dre);
  WgRS<32>::mma<HI_SW64>(d, a[1], dim);
  WgRS<32>::mma<HI_SW64>(d + 16, a[3], dim);
  wg_commit();
}

__device__ __forceinline__ void conv_channel(const FftConst& k, uint32_t sb, int c, int wg, int w, int lane) {
  const uint32_t cb = sb + off_ch(c), bars = sb + OFF_BAR;
  const uint32_t du = desc_lo(cb, 1024), dg = desc_lo(sb + OFF_GT, 16), dz = desc_lo(cb + U_BYTES, 16);
  float U[32], H[32];
  uint32_t a[4][4], e[4][4];
  const float dv = __uint_as_float(lds32(sb + OFF_D + 4 * c));
  wg_fence();
  WgRS<64>::set<HI_SW32>(H, k.f[0], du + 256);
  WgRS<64>::mma<HI_SW32>(H, k.f[1], du + 256 + 32);
  wg_commit();
  wg_wait<0>();
  pin<32>(H);
  twiddle_fwd(a, H, k);
  if (ATT_GATE && H_EARLY) mbar_wait(bars + 8 * B_ATTN, 0);
  mbar_wait(bars + 8 * (B_U + (c < 3 ? c : 3)), 0);
  TSM(w == 0 && c < 3, 7 + wg);
  wg_fence();
  WgRS<64>::set<HI_SW32>(U, k.f[0], du);
  WgRS<64>::mma<HI_SW32>(U, k.f[1], du + 32);
  wg_commit();
  g_step(H, a, dg, dg + 64);
  wg_wait<1>();
  pin<32>(U);
  twiddle_fwd(e, U, k);
  wg_fence();
  g_step(U, e, dg, dg + 64);
  wg_wait<0>();
  pin<32>(U);
  pin<32>(H);
#pragma unroll
  for (int j = 0; j < 2; j++) {
    float pr[4][2], pi[4][2];
#pragma unroll
    for (int x = 0; x < 2; x++) {
      H[4 * j + x] += dv;
#pragma unroll
      for (int m = 0; m < 4; m++) {
#pragma unroll
        for (int q = 0; q <= m; q++) {
          const int ih = 16 * (q >> 1) + 2 * (q & 1) + 4 * j + x, iu = 16 * ((m - q) >> 1) + 2 * ((m - q) & 1) + 4 * j + x;
          pr[m][x] = q ? fmaf(H[ih], U[iu], pr[m][x]) : H[ih] * U[iu];
          pi[m][x] = q ? fmaf(H[ih], U[iu + 8], pi[m][x]) : H[ih] * U[iu + 8];
          pr[m][x] = fmaf(-H[ih + 8], U[iu + 8], pr[m][x]);
          pi[m][x] = fmaf(H[ih + 8], U[iu], pi[m][x]);
        }
      }
    }
#pragma unroll
    for (int m = 0; m < 4; m++) {
      a[m & 2][2 * j + (m & 1)] = pack2(pr[m][0], pr[m][1]);
      a[(m & 2) + 1][2 * j + (m & 1)] = pack2(pi[m][0], pi[m][1]);
    }
  }
  wg_fence();
  g_step(U, a, dg + 64, dg);
  const uint32_t za = cb + U_BYTES + (8 * w + (lane & 7)) * 128 + (((lane >> 3) ^ (lane & 7)) << 4);
  const uint32_t ya = cb + (lane >> 4) * 1024 + (8 * w + (lane & 7)) * 32 + ((((lane >> 3) ^ (lane >> 2)) & 1) << 4);
  wg_sync(1 + wg);
  wg_wait<0>();
  pin<32>(U);
  TSIF(w == 0, 80 + c);
#pragma unroll
  for (int p = 0; p < 2; p++) {
#pragma unroll
    for (int i = 0; i < 4; i++) {
      const int j = i & 1;
      float* x = U + 16 * p + 4 * j + (i & 2);
      rot<true>(x[8], x[0], k.ta[2 * j], k.tb[2 * j]);
      rot<true>(x[9], x[1], k.ta[2 * j + 1], k.tb[2 * j + 1]);
      e[p][i] = pack2(x[8], x[9]);
      e[2 + p][i] = pack2(x[0], x[1]);
    }
    stsm4(za ^ (64 * p), e[p]);
    stsm4((za ^ (64 * p)) + 4096, e[2 + p]);
  }
  fence_async_smem();
  wg_sync(1 + wg);
  wg_fence();
  WgRS<64>::set<HI_SW128>(H, k.fi[0], dz);
#pragma unroll
  for (int ks = 1; ks < 4; ks++) WgRS<64>::mma<HI_SW128>(H, k.fi[ks], dz + 128 * ks);
  wg_commit();
  wg_wait<0>();
  pin<32>(H);
  TSIF(w == 0, 88 + c);
#pragma unroll
  for (int j = 0; j < 8; j++)
    a[j >> 2][j & 3] = j < 2 ? pack2(H[4 * j], H[4 * j + 1]) : pack2(H[4 * j] + H[4 * j - 6], H[4 * j + 1] + H[4 * j - 5]);
  stsm4(ya, a[0]);
  stsm4(ya + 2048, a[1]);
  fence_async_smem();
  __syncwarp();
}

__device__ __forceinline__ void prep_slab(uint4* res, const uint2* sw, uint32_t sb, int slab, int w, int lane) {
  const int t = lane & 3, tp = (lane & 7) >> 1, pos = 8 * tp + 2 * (((lane >> 3) + tp) & 3) + (lane & 1);
  const uint32_t base = sb + OFF_KVS + slab * KVS_BYTES + pos * 128;
  uint32_t kk[2][4][4], vv[2][4];
  mbar_wait(sb + OFF_BAR + 8 * (B_KV + slab), 0);
#pragma unroll
  for (int h = 0; h < 2; h++) {
#pragma unroll
    for (int j = 0; j < 4; j++) {
      const uint32_t a = base + 128 * j;
      ldsm4t(kk[h][j], a + (((w + 4 * h) ^ ((a >> 7) & 7)) << 4));
    }
    const uint32_t a = base + KVS_V;
    ldsm4t(vv[h], a + (((w + 4 * h) ^ ((a >> 7) & 7)) << 4));
  }
#pragma unroll
  for (int h = 0; h < 2; h++) {
    uint32_t (&k)[4][4] = kk[h];
    uint32_t (&v)[4] = vv[h];
    const uint32_t w0 = __byte_perm(sw[h].x, 0, 0x1010), w1 = __byte_perm(sw[h].x, 0, 0x3232);
    const uint32_t w2 = __byte_perm(sw[h].y, 0, 0x1010), w3 = __byte_perm(sw[h].y, 0, 0x3232);
#pragma unroll
    for (int m = 0; m < 4; m++)
      v[m] = bmul(badd(badd(badd(bmul(k[0][m], w3), bmul(k[1][m], w2)), bmul(k[2][m], w1)), bmul(k[3][m], w0)), v[m]);
    uint32_t a[4];
#pragma unroll
    for (int m = 0; m < 4; m++) a[m] = (t & 1) ? v[(m + 3) & 3] : v[m];
    res[h] = (t & 2) ? make_uint4(a[2], a[3], a[0], a[1]) : make_uint4(a[0], a[1], a[2], a[3]);
  }
}

__device__ __forceinline__ void prep_gate(const Params& p, int b, int w, int lane) {
  uint2 gw[5], x[4][5];
#pragma unroll
  for (int j = 0; j < 5; j++) gw[j] = ldg64(reinterpret_cast<const uint2*>(p.gate_w) + lane + 32 * j);
#pragma unroll
  for (int i = 0; i < 4; i++)
#pragma unroll
    for (int j = 0; j < 5; j++)
      x[i][j] = ldg64(reinterpret_cast<const uint2*>(p.q) + (16 * b + 4 * w + i) * (DIM / 4) + lane + 32 * j);
  float s[4];
#pragma unroll
  for (int i = 0; i < 4; i++) {
    s[i] = 0.f;
#pragma unroll
    for (int j = 0; j < 5; j++) {
      const uint32_t m0 = bmul(x[i][j].x, gw[j].x), m1 = bmul(x[i][j].y, gw[j].y);
      s[i] += (bf_lo(m0) + bf_hi(m0)) + (bf_lo(m1) + bf_hi(m1));
    }
  }
  const bool h = lane & 16, q = lane & 8;
  const float a = (h ? s[2] : s[0]) + __shfl_xor_sync(0xffffffffu, h ? s[0] : s[2], 16);
  const float c = (h ? s[3] : s[1]) + __shfl_xor_sync(0xffffffffu, h ? s[1] : s[3], 16);
  float z = (q ? c : a) + __shfl_xor_sync(0xffffffffu, q ? a : c, 8);
#pragma unroll
  for (int o = 4; o > 0; o >>= 1) z += __shfl_xor_sync(0xffffffffu, z, o);
  z = bf_lo(pack2(z, 0.f));
  if ((lane & 7) == 0) g_gate[16 * b + 4 * w + (lane >> 3)] = bf_lo(pack2(__fdividef(1.f, 1.f + __expf(-z)), 0.f));
}

__device__ __forceinline__ uint32_t bmax(uint32_t a, uint32_t b) {
  uint32_t d;
  asm("max.bf16x2 %0, %1, %2;" : "=r"(d) : "r"(a), "r"(b));
  return d;
}
__device__ __forceinline__ void softmax_two(const float (&l)[2][2], uint32_t& p0, uint32_t& p1) {
  constexpr float kScale = 0.22360679774997896f, kLog2e = 1.4426950408889634f;
  const uint32_t r0 = pack2(l[0][0], l[1][0]), r1 = pack2(l[0][1], l[1][1]);
  const uint32_t x0 = pack2(bf_lo(r0) * kScale, bf_hi(r0) * kScale), x1 = pack2(bf_lo(r1) * kScale, bf_hi(r1) * kScale);
  uint32_t m = bmax(x0, x1);
  m = bmax(m, __shfl_xor_sync(0xffffffffu, m, 1));
  m = bmax(m, __shfl_xor_sync(0xffffffffu, m, 2));
  const float m0 = bf_lo(m) * kLog2e, m1 = bf_hi(m) * kLog2e;
  p0 = pack2(ex2(bf_lo(x0) * kLog2e - m0), ex2(bf_lo(x1) * kLog2e - m0));
  p1 = pack2(ex2(bf_hi(x0) * kLog2e - m1), ex2(bf_hi(x1) * kLog2e - m1));
}

__device__ __forceinline__ void halo_read(uint32_t (&kpv)[10], uint32_t (&vpv)[10], uint32_t (&tg)[7], const uint4* hp) {
#pragma unroll
  for (int j = 0; j < 7; j++) {
    uint32_t x0, x1, x2;
    asm volatile("ld.relaxed.gpu.global.v4.u32 {%0, %1, %2, %3}, [%4];"
                 : "=r"(x0), "=r"(x1), "=r"(x2), "=r"(tg[j]) : "l"(hp + 32 * j) : "memory");
    if (j < 4) kpv[3 * j] = x0; else vpv[3 * j - 10] = x0;
    if (j < 3) kpv[3 * j + 1] = x1; else vpv[3 * j - 9] = x1;
    if (j < 3) kpv[3 * j + 2] = x2; else if (j < 6) vpv[3 * j - 8] = x2;
  }
}

template <int ROT>
__device__ __forceinline__ void pack_qkv(const float* acc, uint32_t (&qlo)[10], uint32_t (&qhi)[10], uint32_t (&klo)[10],
                                         uint32_t (&khi)[10], uint32_t (&vlo)[10], uint32_t (&vhi)[10]) {
#pragma unroll
  for (int j = 0; j < 10; j++) {
    const int x = (j + ROT) % 10, tq = x < 8 ? x : 16 + x, tk = x < 8 ? 8 + x : 18 + x, tv = x < 8 ? 16 + x : 20 + x;
    khi[j] = pack2(acc[4 * tk + 2], acc[4 * tk + 3]);
    vhi[j] = movm(pack2(acc[4 * tv + 2], acc[4 * tv + 3]));
    qlo[j] = pack2(acc[4 * tq], acc[4 * tq + 1]);
    qhi[j] = pack2(acc[4 * tq + 2], acc[4 * tq + 3]);
    klo[j] = pack2(acc[4 * tk], acc[4 * tk + 1]);
    vlo[j] = pack2(acc[4 * tv], acc[4 * tv + 1]);
    asm volatile("" : "+r"(khi[j]), "+r"(qlo[j]), "+r"(qhi[j]), "+r"(klo[j]), "+r"(vlo[j]));
  }
}

template <int ROT> __device__ __forceinline__ void halo_send(const float* acc, uint4* ho, uint32_t tag) {
#pragma unroll
  for (int j = 0; j < 7; j++) {
    uint32_t x[3];
#pragma unroll
    for (int e = 0; e < 3; e++) {
      const int i = 3 * j + e, y = (i % 10 + ROT) % 10, tk = y < 8 ? 8 + y : 18 + y, tv = y < 8 ? 16 + y : 20 + y;
      x[e] = i < 10 ? pack2(acc[4 * tk + 2], acc[4 * tk + 3]) : i < 20 ? movm(pack2(acc[4 * tv + 2], acc[4 * tv + 3])) : 0u;
    }
    asm volatile("st.relaxed.gpu.global.v4.u32 [%0], {%1, %2, %3, %4};" ::"l"(ho + 32 * j), "r"(x[0]), "r"(x[1]), "r"(x[2]), "r"(tag) : "memory");
  }
}

__device__ __forceinline__ void attention(float* acc, uint32_t sb, int b, int par, int w, int lane, uint32_t tag) {
  const int g = lane >> 2, t = lane & 3;
  uint32_t klo[10], khi[10], vlo[10], vhi[10], qlo[10], qhi[10], kpv[10], vpv[10];
  if (HALO_FIRST && w == 3 && b < NCTA - 8) {
    uint4* ho = g_halo + (b * 2 + par) * 224 + lane;
    if (tail_first(b & 7)) halo_send<8>(acc, ho, tag);
    else halo_send<0>(acc, ho, tag);
    TSIF(par == 0, 76);
    pin<120>(acc);
  }
  if (tail_first(b & 7)) pack_qkv<8>(acc, qlo, qhi, klo, khi, vlo, vhi);
  else pack_qkv<0>(acc, qlo, qhi, klo, khi, vlo, vhi);
  const uint32_t xa = sb + OFF_KVX + (par * 3) * 2560 + lane * 16;
  if (w < 3) {
    sts128(xa + w * 2560, khi[0], khi[1], khi[2], khi[3]);
    sts128(xa + w * 2560 + 512, khi[4], khi[5], khi[6], khi[7]);
    sts128(xa + w * 2560 + 1024, khi[8], khi[9], vhi[0], vhi[1]);
    sts128(xa + w * 2560 + 1536, vhi[2], vhi[3], vhi[4], vhi[5]);
    sts128(xa + w * 2560 + 2048, vhi[6], vhi[7], vhi[8], vhi[9]);
  } else if (!HALO_FIRST && b < NCTA - 8) {
    uint4* ho = g_halo + (b * 2 + par) * 224 + lane;
#pragma unroll
    for (int j = 0; j < 7; j++) {
      const uint32_t x0 = j < 4 ? khi[3 * j] : vhi[3 * j - 10], x1 = j < 3 ? khi[3 * j + 1] : vhi[3 * j - 9];
      const uint32_t x2 = j < 3 ? khi[3 * j + 2] : j < 6 ? vhi[3 * j - 8] : 0u;
      asm volatile("st.relaxed.gpu.global.v4.u32 [%0], {%1, %2, %3, %4};" ::"l"(ho + 32 * j), "r"(x0), "r"(x1), "r"(x2), "r"(tag) : "memory");
    }
  }
  TSIF(par == 0 && w == 1, 64);
  TSIF(par == 0 && w == 3 && !HALO_FIRST, 76);
#pragma unroll
  for (int j = 0; j < 10; j++) vlo[j] = movm(vlo[j]);
  const bool far0 = 2 * t > g, far1 = 2 * t + 1 > g;
  const uint32_t mfar = (far0 ? 0x0000FFFFu : 0u) | (far1 ? 0xFFFF0000u : 0u);
  float slo[4][2], shi[4][2], lg[2][2];
  uint32_t phi[4], plo[4], qml[4], qmh[4];
#pragma unroll
  for (int h = 0; h < 4; h++) {
    const int f = h == 0 ? 0 : h == 1 ? 3 : h == 2 ? 5 : 8, hf = h < 2 ? 2 : 7;
    const bool mine = (h & 1) ? t >= 2 : t < 2;
    qml[h] = mine ? qlo[hf] : 0u;
    qmh[h] = mine ? qhi[hf] : 0u;
    float a[4] = {0.f, 0.f, 0.f, 0.f}, c[4] = {0.f, 0.f, 0.f, 0.f};
    mma16816(a, qlo[f], qhi[f], qlo[f + 1], qhi[f + 1], klo[f], klo[f + 1]);
    mma16816(c, qlo[f], qhi[f], qlo[f + 1], qhi[f + 1], khi[f], khi[f + 1]);
    mma1688(a, qml[h], qmh[h], klo[hf]);
    mma1688(c, qml[h], qmh[h], khi[hf]);
    slo[h][0] = a[0];
    slo[h][1] = a[1];
    shi[h][0] = lg[h & 1][0] = far0 ? a[2] : c[2];
    shi[h][1] = lg[h & 1][1] = far1 ? a[3] : c[3];
    if (!ATT_MERGE && (h & 1)) softmax_two(lg, phi[h - 1], phi[h]);
  }
  TSIF(par == 0 && w == 1, 65);
  wg_sync(1 + par);
  TSIF(par == 0 && w == 1, 66);
  const bool nohist = (w == 0) && (b < 8);
  const uint4* hp = g_halo + ((b - 8) * 2 + par) * 224 + lane;
  uint32_t tg[7];
  if (w > 0) {
    const uint4 v0 = lds128(xa + (w - 1) * 2560), v1 = lds128(xa + (w - 1) * 2560 + 512), v2 = lds128(xa + (w - 1) * 2560 + 1024);
    const uint4 v3 = lds128(xa + (w - 1) * 2560 + 1536), v4 = lds128(xa + (w - 1) * 2560 + 2048);
    kpv[0] = v0.x; kpv[1] = v0.y; kpv[2] = v0.z; kpv[3] = v0.w; kpv[4] = v1.x; kpv[5] = v1.y; kpv[6] = v1.z; kpv[7] = v1.w;
    kpv[8] = v2.x; kpv[9] = v2.y; vpv[0] = v2.z; vpv[1] = v2.w; vpv[2] = v3.x; vpv[3] = v3.y; vpv[4] = v3.z; vpv[5] = v3.w;
    vpv[6] = v4.x; vpv[7] = v4.y; vpv[8] = v4.z; vpv[9] = v4.w;
  } else if (nohist) {
#pragma unroll
    for (int j = 0; j < 10; j++) kpv[j] = vpv[j] = 0u;
  } else {
    TSIF(par == 0, 77);
    halo_read(kpv, vpv, tg, hp);
  }
  if (w == 0 && !nohist) {
    int spins = 0;
    while (true) {
      bool ok = true;
#pragma unroll
      for (int j = 0; j < 7; j++) ok = ok && tg[j] == tag;
      if (__all_sync(0xffffffffu, ok) || ++spins > SPIN_LIMIT) break;
      halo_read(kpv, vpv, tg, hp);
    }
    TSIF(par == 0, 79);
  }
#pragma unroll
  for (int h = 0; h < 4; h++) {
    const int f = h == 0 ? 0 : h == 1 ? 3 : h == 2 ? 5 : 8, hf = h < 2 ? 2 : 7;
    float a[4] = {0.f, 0.f, 0.f, 0.f};
    mma16816(a, qlo[f], qhi[f], qlo[f + 1], qhi[f + 1], kpv[f], kpv[f + 1]);
    mma1688(a, qml[h], qmh[h], kpv[hf]);
    const float ninf = __int_as_float(0xff800000);
    lg[h & 1][0] = far0 ? (nohist ? ninf : a[0]) : slo[h][0];
    lg[h & 1][1] = far1 ? (nohist ? ninf : a[1]) : slo[h][1];
    if (h & 1) {
      softmax_two(lg, plo[h - 1], plo[h]);
      if (ATT_MERGE) {
        const float lh[2][2] = {{shi[h - 1][0], shi[h - 1][1]}, {shi[h][0], shi[h][1]}};
        softmax_two(lh, phi[h - 1], phi[h]);
      }
    }
  }
  TSIF(par == 0 && w <= 1, 67 + w);
  uint32_t ov[20];
#pragma unroll
  for (int hp = 0; hp < 2; hp++) {
    const int hf = hp ? 7 : 2;
    float sh[4] = {0.f, 0.f, 0.f, 0.f}, i0 = 0.f, i1 = 0.f;
#pragma unroll
    for (int e = 0; e < 2; e++) {
      const int h = 2 * hp + e, f = h == 0 ? 0 : h == 1 ? 3 : h == 2 ? 5 : 8;
      const uint32_t a0 = plo[h] & mfar, a2 = plo[h] & ~mfar, a3 = phi[h] & mfar, c1 = phi[h] & ~mfar;
      float sum[4] = {0.f, 0.f, 0.f, 0.f};
      mma1688(sum, plo[h], phi[h], 0x3F803F80u);
      const float r0 = rcp(sum[0]), r1 = rcp(sum[2]);
#pragma unroll
      for (int j = f; j < f + 2; j++) {
        float o[4] = {0.f, 0.f, 0.f, 0.f};
        mma16816(o, a0, 0u, a2, a3, vpv[j], vlo[j]);
        mma1688(o, 0u, c1, vhi[j]);
        ov[2 * j] = pack2(o[0] * r0, o[1] * r0);
        ov[2 * j + 1] = pack2(o[2] * r1, o[3] * r1);
      }
      const bool mine = e ? g >= 4 : g < 4;
      mma16816(sh, a0, 0u, a2, a3, mine ? vpv[hf] : 0u, mine ? vlo[hf] : 0u);
      mma1688(sh, 0u, c1, mine ? vhi[hf] : 0u);
      if (e == 0 || t >= 2) {
        i0 = r0;
        i1 = r1;
      }
    }
    ov[2 * hf] = pack2(sh[0] * i0, sh[1] * i0);
    ov[2 * hf + 1] = pack2(sh[2] * i1, sh[3] * i1);
  }
  TS(32 + 4 * par + w);
  mbar_wait(sb + OFF_BAR + 8 * B_P1, 0);
  const uint32_t oa = sb + OFF_OA + (lane >> 4) * 2048 + (32 * w + 2 * (lane & 15) + par) * 16;
#pragma unroll
  for (int j = 0; j < 5; j++) stsm4(oa + 4096 * j, ov + 4 * j);
  TSIF(par == 0 && w == 0, 120);
  fence_async_smem();
  TSIF(par == 0 && w == 0, 121);
  __syncwarp();
  if (lane == 0) mbar_arrive(sb + OFF_BAR + 8 * B_ATTN);
  TSIF(par == 0 && w == 0, 122);
}

struct Maps {
  CUtensorMap x, wm, wt, k, v, y, wo, qm, qt, om, ot, u;
};

__device__ __forceinline__ void load_stage(uint32_t sb, int kb, int b, const Maps& m) {
  const uint32_t st = sb + (kb & 3) * STAGE_BYTES, bar = sb + OFF_BAR + 8 * (B_FULL1 + (kb & 3));
  const int r = b >> 3, hg = b & 7, slab = kb - KV_KB;
  const bool kv = slab >= 0 && slab < 5;
  const uint32_t kbar = sb + OFF_BAR + 8 * (B_KV + slab), dst = sb + OFF_KVS + slab * KVS_BYTES;
  mbar_expect_tx(bar, STAGE_BYTES);
  if (kv) mbar_expect_tx(kbar, KVS_BYTES);
  tma_3d(st, &m.x, 64 * kb, 64 * r, 0, bar);
  if (kv && KV_MIX) tma_3d(dst, &m.k, 0, 32 * (b >> 1) - 3, 2 * slab + (b & 1), kbar);
  tma_3d(st + ST_W, &m.wm, 80 * hg + (tail_first(hg) ? 16 : 0), 64 * kb, 0, bar);
  if (kv && KV_MIX) tma_3d(dst + KVS_V, &m.v, 0, 32 * (b >> 1), 2 * slab + (b & 1), kbar);
  tma_3d(st + ST_WT, &m.wt, 80 * hg + (tail_first(hg) ? 0 : 64), 64 * kb, 0, bar);
  if (kv && !KV_MIX) tma_3d(dst, &m.k, 0, 32 * (b >> 1) - 3, 2 * slab + (b & 1), kbar);
  if (kv && !KV_MIX) tma_3d(dst + KVS_V, &m.v, 0, 32 * (b >> 1), 2 * slab + (b & 1), kbar);
}

__global__ void __launch_bounds__(NTHR, 1) fused_kernel(const __grid_constant__ Maps m, const Params p) {
  extern __shared__ __align__(1024) uint8_t smem[];
  const uint32_t sb = (uint32_t)__cvta_generic_to_shared(smem);
  const uint32_t bars = sb + OFF_BAR;
  const int tid = threadIdx.x, lane = tid & 31;
  int b = blockIdx.x;
  if (BMAP == 1) b = (((b & 63) >> 3) * 2 + (b & 1)) * 8 + (((b < 64 ? 0x6521 : 0x7430) >> (4 * ((b >> 1) & 3))) & 7);
  if (BMAP == 2) b = ((b & 63) >> 2) * 8 + (((b < 64 ? 0x6521 : 0x7430) >> (4 * (b & 3))) & 7);
  if (BMAP == 3) b = (((b & 63) >> 3) * 2 + (b & 1)) * 8 + (((b < 64 ? 0x7430 : 0x6521) >> (4 * ((b >> 1) & 3))) & 7);
  if (BMAP == 4) b = (((b >> 4) * 2 + (b & 1)) * 8) + ((b >> 1) & 7);
  if (BMAP == 5) b = 127 - b;
  const int r = b >> 3, hg = b & 7;

  if (tid == T_ISSUE) {
    TSM(true, 0);
#pragma unroll
    for (int i = 0; i < 4; i++) mbar_init(bars + 8 * (B_FULL1 + i), 1);
#pragma unroll
    for (int i = 0; i < 3; i++) mbar_init(bars + 8 * (B_KV + i), 1);
    fence_async_smem();
#pragma unroll 1
    for (int kb = 0; kb <= PRE2; kb++) load_stage(sb, kb, b, m);
  } else if (tid >= T_PF && tid < T_PF + 12) {
    tm_prefetch(&m.x + (tid - T_PF));
  } else if (tid == T_INIT) {
#pragma unroll
    for (int i = 0; i < 4; i++) mbar_init(bars + 8 * (B_EMPTY1 + i), 8);
#pragma unroll
    for (int i = 0; i < 8; i++) mbar_init(bars + 8 * (B_FULL2 + i), 1);
#pragma unroll
    for (int i = 0; i < 4; i++) mbar_init(bars + 8 * (B_EMPTY2 + i), 8);
#pragma unroll
    for (int i = 0; i < 4; i++) mbar_init(bars + 8 * (B_U + i), 1);
    mbar_init(bars + 8 * B_HA, 4);
    mbar_init(bars + 8 * B_GATE, 4);
    mbar_init(bars + 8 * B_HB, 1);
    mbar_init(bars + 8 * B_KVD, 4);
    mbar_init(bars + 8 * B_QF, 1);
    mbar_init(bars + 8 * B_ATTN, 8);
    mbar_init(bars + 8 * B_P1, 8);
    mbar_init(bars + 8 * B_C34, 1);
#pragma unroll
    for (int i = 0; i < 5; i++) mbar_init(bars + 8 * (B_YST + i), 4);
#pragma unroll
    for (int i = 0; i < 5; i++) mbar_init(bars + 8 * (B_US + i), 4);
    mbar_init(bars + 8 * B_YSIG, 1);
    mbar_init(bars + 8 * B_YFULL, 1);
    mbar_init(bars + 8 * B_EPOCH, 1);
    mbar_init(bars + 8 * B_PREP, 4);
    mbar_init(bars + 8 * B_USIG, 1);
    mbar_init(bars + 8 * B_WST, 1);
#pragma unroll
    for (int i = 3; i < 5; i++) mbar_init(bars + 8 * (B_KV + i), 1);
    mbar_init(bars + 8 * B_E3, 8);
    mbar_init(bars + 8 * B_LAST, 1);
    mbar_init(bars + 8 * B_OSIG, 1);
    mbar_init(bars + 8 * B_WOP, 1);
    fence_async_smem();
  }
  const int warp = __shfl_sync(0xffffffffu, tid >> 5, 0), wg = warp >> 2, w = warp & 3;
  __syncthreads();

  if (wg == 3) {
    asm volatile("setmaxnreg.dec.sync.aligned.u32 56;");
    if (w == 0) {
      if (lane == 0) {
#pragma unroll 1
        for (int kb = 1 + PRE2; kb < 10; kb++) {
          if (kb >= 4) mbar_wait(bars + 8 * (kb == 7 ? B_E3 : B_EMPTY1 + (kb & 3)), (kb >> 3) & 1);
          TSIF(kb >= 4, 44 + kb);
          load_stage(sb, kb, b, m);
          TSIF(kb == 3, 60);
          if (kb == TRIG_KB) mbar_arrive(bars + 8 * B_LAST);
        }
        mbar_wait(bars + 8 * B_WOP, 0);
        mbar_wait(bars + 8 * WL_TRIG, 0);
        mbar_wait(bars + 8 * B_EPOCH, 0);
        flag_wait(g_cnt + C_W + 32 * hg, (lds32(sb + OFF_EPOCH) + 1) * 16);
        TS(30);
#pragma unroll 1
        for (int j = 0; j < 8; j++) {
          if (j >= 6) mbar_wait(bars + 8 * (B_EMPTY2 + j - 6), 0);
          if (j == 4) mbar_wait(bars + 8 * B_ATTN, 0);
          TSIF(j >= 6, 100 + j);
          if (RF_GATE && j == 6) mbar_wait(bars + 8 * B_YSIG, 0);
          mbar_expect_tx(bars + 8 * (B_FULL2 + j), j == 0 ? WO_BYTES : j == 5 ? O_BYTES + WO_BYTES + 512 : O_BYTES + WO_BYTES);
          bulk_load(sb + off_w(j), g_WO + (hg * 8 + step_src(hg, j)) * 800, WO_BYTES, bars + 8 * (B_FULL2 + j));
        }
        mbar_wait(bars + 8 * (B_EMPTY2 + 3), 0);
        mbar_expect_tx(bars + 8 * B_QF, O_BYTES);
        tma_2d(sb + OFF_QS, &m.qm, 80 * hg, 128 * r, bars + 8 * B_QF);
        tma_2d(sb + OFF_QT, &m.qt, 80 * hg + 64, 128 * r, bars + 8 * B_QF);
      }
    } else if (w == 1) {
      unsigned epoch = 0;
      if (lane == 0) {
        epoch = atomicAdd(g_cnt + C_LAUNCH, 1u) / NCTA;
        asm volatile("st.shared.u32 [%0], %1;" ::"r"(sb + OFF_EPOCH), "r"(epoch) : "memory");
        mbar_arrive(bars + 8 * B_EPOCH);
        mbar_wait(bars + 8 * B_KVD, 0);
        mbar_expect_tx(bars + 8 * B_HB, 5 * 4096);
#pragma unroll 1
        for (int c = 0; c < 5; c++) {
          if (c == 3) mbar_wait(bars + 8 * B_S3, 0);
          bulk_load(sb + off_ch(c) + U_BYTES, p.ssm_k + (5 * b + c) * SEQ, 4096, bars + 8 * B_HB);
        }
#pragma unroll
        for (int c = 0; c < 4; c++) mbar_expect_tx(bars + 8 * (B_U + c), c < 3 ? U_BYTES : 2 * U_BYTES);
        const uint4* usrc = g_U + 5 * b * U_PITCH;
        mbar_wait(bars + 8 * B_USIG, 0);
        flag_wait(g_cnt + C_PREP + 32 * (b & 15), (epoch + 1) * NCTA);
        TS(23);
#pragma unroll
        for (int c = 0; c < 5; c++) {
          if (c == 3) mbar_wait(bars + 8 * (B_U + 2), 0);
          bulk_load(sb + off_ch(c), usrc + c * U_PITCH, U_BYTES, bars + 8 * (B_U + (c < 3 ? c : 3)));
          TSIF(c == 0 || c == 4, 116 + (c >> 2));
        }
      }
      epoch = __shfl_sync(0xffffffffu, epoch, 0);
      if (lane < 8) {
        const int src = (b & ~7) | step_src(hg, lane);
        mbar_wait(bars + 8 * B_OSIG, 0);
        TS(20);
        flag_wait(g_cnt + C_O + 32 * src, epoch + 1);
        if (lane >= 1 && lane < 4) bulk_load(sb + off_o(lane), g_O + src * 1280, O_BYTES, bars + 8 * (B_FULL2 + lane));
        __syncwarp(0xff);
        TS(21);
        if (lane == 5) bulk_load(sb + OFF_GATE, g_gate + 128 * r, 512, bars + 8 * (B_FULL2 + 5));
#pragma unroll 1
        for (int j = 4; j < 8; j++) {
          if (lane == j) {
            mbar_wait(bars + 8 * (j < 6 ? B_C34 : B_EMPTY2 + j - 6), 0);
            if (RF_GATE && j == 6) mbar_wait(bars + 8 * B_YSIG, 0);
            bulk_load(sb + off_o(j), g_O + src * 1280, O_BYTES, bars + 8 * (B_FULL2 + j));
          }
          __syncwarp(0xff);
        }
        TS(22);
      }
    } else if (w == 2) {
      mbar_wait(bars + 8 * B_PREP, 0);
      flag_signal(g_cnt + C_PREP, 16, lane);
      TS(25);
      if (lane == 0) mbar_arrive(bars + 8 * B_USIG);
      mbar_wait(bars + 8 * B_GATE, 0);
      if ((NOMB & 1) && lane == 0) asm volatile("fence.release.gpu;" ::: "memory");
      mbar_wait(bars + 8 * B_ATTN, 0);
      if (lane == 0) {
        if (O_DEFER) mbar_wait(bars + 8 * (B_U + 3), 0);
        asm volatile("cp.async.bulk.global.shared::cta.bulk_group [%0], [%1], 20480;\ncp.async.bulk.commit_group;\n"
                     "cp.async.bulk.wait_group 0;\nfence.proxy.async.global;" ::"l"(g_O + b * 1280), "r"(sb + OFF_OA) : "memory");
      }
      TS(74);
      if (!(NOMB & 1)) flag_signal(g_cnt + C_O + 32 * b, 1, lane);
      else if (lane == 0) flag_bump(g_cnt + C_O + 32 * b);
      TS(26);
      if (lane == 0) mbar_arrive(bars + 8 * B_OSIG);

    } else {
      if (lane == 0) {
        uint4* dst = g_WO + (hg * 8 + (r >> 1)) * 800 + (r & 1) * 80;
        mbar_wait(bars + 8 * B_P1, 0);
        mbar_wait(bars + 8 * WB_TRIG, 0);
        mbar_expect_tx(bars + 8 * B_WST, WO_BYTES / 2);
        tma_3d(sb + OFF_WS, &m.wo, 0, 40 * r, 5 * hg, bars + 8 * B_WST);
        mbar_wait(bars + 8 * B_WST, 0);
        mbar_wait(bars + 8 * WO_TRIG, 0);
#pragma unroll 1
        for (int n = 0; n < 5; n++)
          asm volatile("cp.async.bulk.global.shared::cta.bulk_group [%0], [%1], 1280;" ::"l"(dst + 160 * n), "r"(sb + OFF_WS + 1280 * n) : "memory");
        asm volatile("cp.async.bulk.commit_group;\ncp.async.bulk.wait_group 0;\nfence.proxy.async.global;" ::: "memory");
        if (!(NOMB & 4)) asm volatile("fence.release.gpu;" ::: "memory");
        flag_bump(g_cnt + C_W + 32 * hg);
        mbar_arrive(bars + 8 * B_WOP);
        TS(71);
#pragma unroll 1
        for (int c = 0; c < 5; c++) {
          mbar_wait(bars + 8 * (B_YST + c), 0);
          asm volatile("cp.async.bulk.global.shared::cta.bulk_group [%0], [%1], 4096;\ncp.async.bulk.commit_group;"
                       ::"l"(g_Y + (5 * b + c) * Y_PITCH), "r"(sb + off_ch(c)) : "memory");
          if (c == 2) {
            asm volatile("cp.async.bulk.wait_group.read 0;" ::: "memory");
            mbar_arrive(bars + 8 * B_C34);
          }
        }
        asm volatile("cp.async.bulk.wait_group 0;\nfence.proxy.async.global;" ::: "memory");
        TS(75);
        if (!(NOMB & 2)) asm volatile("fence.release.gpu;" ::: "memory");
        flag_bump(g_cnt + C_Y + 32 * (b >> 4));
        TS(27);
        mbar_arrive(bars + 8 * B_YSIG);
        mbar_expect_tx(bars + 8 * B_YFULL, 20480);
        flag_wait(g_cnt + C_Y + 32 * hg, (lds32(sb + OFF_EPOCH) + 1) * 16);
        TS(24);
        tma_2d(sb + OFF_YT, &m.y, 128 * r, 80 * hg, bars + 8 * B_YFULL);
        tma_2d(sb + OFF_YT + 10240, &m.y, 128 * r + 64, 80 * hg, bars + 8 * B_YFULL);
      }
    }
  } else {
    asm volatile("setmaxnreg.inc.sync.aligned.u32 152;");
    if (wg < 2) {
      float acc[120];
#pragma unroll
      for (int i = 0; i < 120; i++) acc[i] = 0.f;
      const uint32_t da = desc_lo(sb + wg * 8192, 16), db = desc_lo(sb + ST_W, 8192), dc = desc_lo(sb + ST_WT, 2048);
      if (PW1) pin<120>(acc);
      if (PW1 == 2) mbar_wait(bars + 8 * B_FULL1, 0);
#pragma unroll 1
      for (int kb = 0; kb < 10; kb++) {
        mbar_wait(bars + 8 * (B_FULL1 + (kb & 3)), (kb >> 2) & 1);
        const uint32_t so = (kb & 3) * (STAGE_BYTES >> 4);
        wg_fence();
#pragma unroll
        for (int k = 0; k < 4; k++) {
          WgSST<192>::mma<HI_SW128, HI_SW128>(acc, da + so + 2 * k, db + so + 128 * k, 1);
          WgSST<48>::mma<HI_SW128, HI_SW32>(acc + 96, da + so + 2 * k, dc + so + 32 * k, 1);
        }
        wg_commit();
        wg_wait<1>();
        if (kb > 0 && lane == 0) mbar_arrive(bars + 8 * (kb == 4 ? B_E3 : B_EMPTY1 + ((kb - 1) & 3)));
      }
      mbar_wait(bars + 8 * B_EPOCH, 0);
      const uint32_t tag = lds32(sb + OFF_EPOCH) + 1;
      mbar_wait(bars + 8 * B_S3, 0);
      wg_wait<0>();
      pin<120>(acc);
      if (lane == 0) mbar_arrive(bars + 8 * B_P1);
      TSM(w == 0, 3 + wg);
      attention(acc, sb, b, wg, w, lane, tag);
    } else {
      const int tw = tid & 127, chl = 64 * (b & 1) + 8 * w + (lane >> 2);
      uint4* up = g_U + chl * U_PITCH + ((4 * (b >> 1) + (lane & 3)) ^ ((b >> 2) & 1));
      uint2 sw[10];
      uint32_t dv = 0;
      if (lane < 5) dv = __ldg(reinterpret_cast<const unsigned short*>(p.ssm_D) + 5 * b + lane);
#pragma unroll
      for (int i = 0; i < 10; i++) sw[i] = ldg64(reinterpret_cast<const uint2*>(p.shift_k) + chl + 128 * (i >> 1) + 32 * (i & 1));
      uint32_t tab[12];
      fft_tables(tab, tw);
      uint4 res[10];
#pragma unroll
      for (int i = 0; i < 10; i++) res[i] = make_uint4(0, 0, 0, 0);
#pragma unroll 1
      for (int slab = 0; slab < 5; slab++) {
#pragma unroll
        for (int i = 0; i < 8; i++) res[i] = res[i + 2];
        prep_slab(res + 8, sw, sb, slab, w, lane);
        TSIF(w == 0, 99 + 4 * slab);
#pragma unroll
        for (int i = 0; i < 8; i++) sw[i] = sw[i + 2];
      }
      TSIF(w == 0, 28);
      __syncwarp();
      if (lane == 0) mbar_arrive(bars + 8 * B_KVD + ((res[8].x ^ res[9].x) & p.zero));
      mbar_wait(bars + 8 * B_KVD, 0);
      fft_tables_store(tab, sb, tw);
      mbar_wait(bars + 8 * B_LAST, 0);
#pragma unroll
      for (int i = 0; i < 10; i++) up[(128 * (i >> 1) + 32 * (i & 1)) * U_PITCH] = res[i];
      __syncwarp();
      if (lane == 0) mbar_arrive(bars + 8 * B_PREP);
      TSIF(w == 0 && !U_TMA, 5);
      mbar_wait(bars + 8 * (G_AFTER ? B_USIG : B_LAST), 0);
      prep_gate(p, b, w, lane);
      __syncwarp();
      if (lane == 0) mbar_arrive(bars + 8 * B_GATE);
      TSIF(w == 0, 72);
      mbar_wait(bars + 8 * B_HB, 0);
      TSIF(w == 0, 123);
      const uint32_t ha = sb + U_BYTES + ((tw >> 3) * 16 + 8 + (tw & 7)) * 16;
      uint4 hv[5];
#pragma unroll
      for (int c = 0; c < 5; c++) hv[c] = lds128(ha + off_ch(c));
      __syncwarp();
#pragma unroll
      for (int c = 0; c < 5; c++) sts128((ha ^ 16) + off_ch(c), hv[c].x, hv[c].y, hv[c].z, hv[c].w);
      if (tw < 5) asm volatile("st.shared.f32 [%0], %1;" ::"r"(sb + OFF_D + 4 * tw), "f"(bf_lo(dv) * 0.125f) : "memory");
      fence_async_smem();
      __syncwarp();
      if (lane == 0) mbar_arrive(bars + 8 * B_HA);
      TSIF(w == 0, 6);
    }

    FftConst fc;
    fft_twiddles(fc, w, lane);
    mbar_wait(bars + 8 * B_HA, 0);
    fft_matrices(fc, sb, w, lane);
    if (ATT_GATE && !H_EARLY) mbar_wait(bars + 8 * B_ATTN, 0);
    TSIF(w == 0 && wg == 2, 124);
#pragma unroll 1
    for (int c = wg == 2 ? 0 : wg + 1; c < 5; c += !CH_W2 ? 3 : wg < 2 ? 5 : c ? 1 : 3) {
      conv_channel(fc, sb, c, wg, w, lane);
      if (lane == 0) mbar_arrive(bars + 8 * (B_YST + c));
      TSM(w == 0, 10 + c);
    }

    if (wg < 2) {
      const int g = lane >> 2;
      float acc[40];
#pragma unroll
      for (int i = 0; i < 40; i++) acc[i] = 0.f;
      const uint32_t da = desc_lo(sb + wg * 1024, 2048), db = desc_lo(sb, 2560);
      mbar_wait(bars + 8 * B_ATTN, 0);
      mbar_wait(bars + 8 * (B_YST + 3), 0);
      mbar_wait(bars + 8 * (B_YST + 4), 0);
      if (PW2) mbar_wait(bars + 8 * B_FULL2, 0);
#pragma unroll 1
      for (int j = 0; j < 8; j++) {
        mbar_wait(bars + 8 * (B_FULL2 + j), 0);
        const uint32_t oa = da + (off_o(j) >> 4), ob = db + (off_w(j) >> 4);
        wg_fence();
#pragma unroll
        for (int k = 0; k < 5; k++) WgSST<80>::mma<HI_NONE, HI_SW32>(acc, oa + 256 * k, ob + 32 * k, 1);
        wg_commit();
        wg_wait<1>();
        if (j >= 1 && j <= 4 && lane == 0) mbar_arrive(bars + 8 * (B_EMPTY2 + j - 1));
      }
      TSIF(w == 0 && wg == 0, 113);
      const int tr = 64 * wg + 16 * w + (lane & 15);
      const uint32_t fm = sb + OFF_QS + tr * 128, fx = (lane >> 4) ^ (tr & 7);
      const uint32_t ft = sb + OFF_QT + tr * 32 + (((lane >> 4) ^ (tr >> 2)) & 1) * 16;
      const float g0 = __uint_as_float(lds32(sb + OFF_GATE + (64 * wg + 16 * w + g) * 4));
      const float g1 = __uint_as_float(lds32(sb + OFF_GATE + (64 * wg + 16 * w + 8 + g) * 4));
      const uint32_t ga = pack2(g0, g0), gb = pack2(g1, g1);
      const uint32_t na = pack2(1.f - g0, 1.f - g0), nb = pack2(1.f - g1, 1.f - g1);

      wg_wait<0>();
      pin<40>(acc);
      TSM(w == 0, 17 + wg);
      uint32_t pb[20];
#pragma unroll
      for (int j = 0; j < 10; j++) {
        pb[2 * j] = bmul(na, pack2(acc[4 * j], acc[4 * j + 1]));
        pb[2 * j + 1] = bmul(nb, pack2(acc[4 * j + 2], acc[4 * j + 3]));
        asm volatile("" : "+r"(pb[2 * j]), "+r"(pb[2 * j + 1]));
      }
      const uint32_t ya = sb + OFF_YT + wg * 10240 + ((lane >> 4) * 8 + (lane & 7)) * 128 +
                          (((2 * w + (((lane >> 3) & 1) ^ wg)) ^ (lane & 7)) << 4);
      uint32_t qf[20];
      mbar_wait(bars + 8 * B_QF, 0);
#pragma unroll
      for (int j = 0; j < 5; j++) ldsm4(qf + 4 * j, j < 4 ? fm + ((fx ^ (2 * j)) << 4) : ft);
      mbar_wait(bars + 8 * B_YFULL, 0);
      TSIF(w == 0 && wg == 0, 19);
#pragma unroll
      for (int j = 0; j < 5; j++) {
        uint32_t y[4];
        ldsm4t(y, ya + 2048 * j);
#pragma unroll
        for (int i = 0; i < 4; i++) qf[4 * j + i] = badd(bmul((i & 1) ? gb : ga, bmul(qf[4 * j + i], y[i])), pb[4 * j + i]);
      }
#pragma unroll
      for (int j = 0; j < 5; j++) stsm4(j < 4 ? fm + ((fx ^ (2 * j)) << 4) : ft, qf + 4 * j);
      fence_async_smem();
      __syncwarp();
      if (lane == 0) {
        const int row = 64 * wg + 16 * w;
        asm volatile("cp.async.bulk.tensor.2d.global.shared::cta.bulk_group [%0, {%2, %3}], [%1];"
                     ::"l"(&m.om), "r"(sb + OFF_QS + row * 128), "r"(80 * hg), "r"(128 * r + row) : "memory");
        asm volatile("cp.async.bulk.tensor.2d.global.shared::cta.bulk_group [%0, {%2, %3}], [%1];"
                     ::"l"(&m.ot), "r"(sb + OFF_QT + row * 32), "r"(80 * hg + 64), "r"(128 * r + row) : "memory");
        asm volatile("cp.async.bulk.commit_group;\ncp.async.bulk.wait_group.read 0;" ::: "memory");
      }
      TSM(true, 40 + 4 * wg + w);
      if (ENDBAR) asm volatile("bar.sync 15, 256;" ::: "memory");
    }
  }
}

typedef CUresult (*EncodeFn)(CUtensorMap*, CUtensorMapDataType, cuuint32_t, void*, const cuuint64_t*, const cuuint64_t*,
                             const cuuint32_t*, const cuuint32_t*, CUtensorMapInterleave, CUtensorMapSwizzle,
                             CUtensorMapL2promotion, CUtensorMapFloatOOBfill);

void encode(EncodeFn fn, CUtensorMap* tm, const void* base, int rank, const cuuint64_t* dims, const cuuint64_t* strides,
            const cuuint32_t* box, CUtensorMapSwizzle swz) {
  const cuuint32_t ones[3] = {1, 1, 1};
  fn(tm, CU_TENSOR_MAP_DATA_TYPE_BFLOAT16, rank, const_cast<void*>(base), dims, strides, box, ones,
     CU_TENSOR_MAP_INTERLEAVE_NONE, swz, CU_TENSOR_MAP_L2_PROMOTION_L2_128B, CU_TENSOR_MAP_FLOAT_OOB_FILL_NONE);
}

}

extern "C" void kernel_launch(void* const* d_in, const int* in_sizes, int n_in, void* d_out, int out_size) {
  (void)in_sizes; (void)n_in; (void)out_size;
  Params p;
  p.q = (const __nv_bfloat16*)d_in[0];
  p.k = (const __nv_bfloat16*)d_in[1];
  p.v = (const __nv_bfloat16*)d_in[2];
  p.shift_k = (const __nv_bfloat16*)d_in[3];
  p.ssm_k = (const __nv_bfloat16*)d_in[4];
  p.ssm_D = (const __nv_bfloat16*)d_in[5];
  p.wqkv = (const __nv_bfloat16*)d_in[7];
  p.wo = (const __nv_bfloat16*)d_in[8];
  p.gate_w = (const __nv_bfloat16*)d_in[9];
  p.out = (__nv_bfloat16*)d_out;
  p.zero = 0;

  static EncodeFn fn = nullptr;
  static void *yaddr = nullptr, *uaddr = nullptr;
  if (!fn) {
    cudaDriverEntryPointQueryResult qr;
    void* f = nullptr;
    cudaGetDriverEntryPoint("cuTensorMapEncodeTiled", &f, cudaEnableDefault, &qr);
    fn = (EncodeFn)f;
    cudaGetSymbolAddress(&yaddr, g_Y);
    cudaGetSymbolAddress(&uaddr, g_U);
    cudaFuncSetAttribute(fused_kernel, cudaFuncAttributeMaxDynamicSharedMemorySize, SMEM_BYTES);
  }
  Maps m;
  {
    const cuuint64_t dims[3] = {640, 1024, 2}, st[2] = {2560, 1280};
    const cuuint32_t box[3] = {64, 64, 2};
    encode(fn, &m.x, p.q, 3, dims, st, box, CU_TENSOR_MAP_SWIZZLE_128B);
  }
  {
    const cuuint64_t dims[3] = {640, 640, 3}, st[2] = {3840, 1280};
    const cuuint32_t box[3] = {64, 64, 3}, boxt[3] = {16, 64, 3};
    encode(fn, &m.wm, p.wqkv, 3, dims, st, box, CU_TENSOR_MAP_SWIZZLE_128B);
    encode(fn, &m.wt, p.wqkv, 3, dims, st, boxt, CU_TENSOR_MAP_SWIZZLE_32B);
  }
  {
    const cuuint64_t dims[3] = {64, 2048, 10}, st[2] = {1280, 128};
    const cuuint32_t boxk[3] = {64, 35, 1}, boxv[3] = {64, 32, 1};
    encode(fn, &m.k, p.k, 3, dims, st, boxk, CU_TENSOR_MAP_SWIZZLE_128B);
    encode(fn, &m.v, p.v, 3, dims, st, boxv, CU_TENSOR_MAP_SWIZZLE_128B);
  }
  {
    const cuuint64_t dims[3] = {16, 640, 40}, st[2] = {1280, 32};
    const cuuint32_t box[3] = {16, 40, 5};
    encode(fn, &m.wo, p.wo, 3, dims, st, box, CU_TENSOR_MAP_SWIZZLE_32B);
  }
  {
    const cuuint64_t dims[2] = {2048, 640}, st[1] = {Y_PITCH * 16};
    const cuuint32_t box[2] = {64, 80};
    encode(fn, &m.y, yaddr, 2, dims, st, box, CU_TENSOR_MAP_SWIZZLE_128B);
    const cuuint64_t stu[1] = {U_PITCH * 16};
    const cuuint32_t boxu[2] = {32, 64};
    encode(fn, &m.u, uaddr, 2, dims, stu, boxu, CU_TENSOR_MAP_SWIZZLE_NONE);
  }
  {
    const cuuint64_t dims[2] = {640, 2048}, st[1] = {1280};
    const cuuint32_t bqm[2] = {64, 128}, bqt[2] = {16, 128}, bom[2] = {64, 16}, bot[2] = {16, 16};
    encode(fn, &m.qm, p.q, 2, dims, st, bqm, CU_TENSOR_MAP_SWIZZLE_128B);
    encode(fn, &m.qt, p.q, 2, dims, st, bqt, CU_TENSOR_MAP_SWIZZLE_32B);
    encode(fn, &m.om, p.out, 2, dims, st, bom, CU_TENSOR_MAP_SWIZZLE_128B);
    encode(fn, &m.ot, p.out, 2, dims, st, bot, CU_TENSOR_MAP_SWIZZLE_32B);
  }
  fused_kernel<<<NCTA, NTHR, SMEM_BYTES>>>(m, p);
}
```

```cpp
#include <cuda.h>
#include <cuda_bf16.h>
#include <cuda_runtime.h>
#include <stdint.h>

namespace {

constexpr int SEQ = 2048, DIM = 640, NCTA = 128, NTHR = 512;

#define TRIG_KB 9
#define KV_KB 2
#define DEV_EXIT 0
#define ATT_GATE 1
#define G_AFTER 0
#define FENCE_LO 0
#define FENCE_HI 0
#define PW1 2
#define PW2 1
#define ENDBAR 0
#define PAD_KB 0
#define Y_ALIAS 1
#define H_EARLY 1
#define NOMB 0
#define SRC_ROT 0
#define WAIT_NS 0
#define WB_TRIG B_USIG
#define G_POS 0
#define TAILF 1
#define T_ISSUE 384
#define T_PF 416
#define T_INIT 448
#define ATT_MERGE 0
#define BMAP 1
#define PRE2 1
#define KV_MIX 0
#define O_DEFER 0
#define CH_W2 0
#define HALO_FIRST 1
#define PREV_EARLY 0
#define ACQ 0
#define U_TMA 0
#define U_GATE 0
#define RF_GATE 0
#define WO_TRIG B_WST
#define WL_TRIG B_WOP
#define WO_GATE 1

constexpr uint32_t STAGE_BYTES = 47104, ST_W = 16384, ST_WT = 40960;
constexpr uint32_t O_BYTES = 20480, WO_BYTES = 12800;
constexpr uint32_t OFF_OA = 0;
constexpr uint32_t OFF_QS = 3 * O_BYTES, OFF_QT = OFF_QS + 16384;
constexpr uint32_t OFF_WC = 81920;
constexpr uint32_t OFF_WA = 94720;
constexpr uint32_t OFF_GATE = 145920;
constexpr uint32_t OFF_KVX = 147968;
constexpr uint32_t OFF_D = OFF_GATE + 512;
constexpr uint32_t OFF_CH3 = 163840;
constexpr uint32_t CH_BYTES = 12288, U_BYTES = 4096;
constexpr uint32_t OFF_FT = 225280, OFF_GT = 229376;
constexpr uint32_t OFF_CH0 = 188416;
constexpr uint32_t OFF_KVS = OFF_CH0, KVS_V = 4480, KVS_BYTES = 8576;
constexpr uint32_t OFF_WS = OFF_WA;
__device__ __forceinline__ uint32_t off_us(int s) { return OFF_CH0 + 4096 * ((0x65320 >> (4 * s)) & 7); }
constexpr uint32_t OFF_YT = 163840;
constexpr uint32_t OFF_BAR = 231936;
constexpr uint32_t SMEM_BYTES = OFF_BAR + 512;

enum : uint32_t {
  B_FULL1 = 0, B_EMPTY1 = 4, B_S3 = 7, B_FULL2 = 52, B_EMPTY2 = 13, B_U = 8, B_GATE = 12, B_HA = 19, B_HB = 20,
  B_ATTN = 21, B_C34 = 22, B_CONV = 23, B_YFULL = 24, B_EPOCH = 25, B_PREP = 26, B_P1 = 27, B_LAST = 28,
  B_E3 = 29, B_OSIG = 30, B_WOP = 31, B_USIG = 32, B_WST = 33, B_KV = 34, B_KVD = 39, B_HC = 61, B_QF = 62, B_YST = 40,
  B_US = 45, B_YSIG = 50
};
constexpr uint32_t OFF_EPOCH = OFF_BAR + 8 * 51;
__device__ __forceinline__ uint32_t off_o(int j) { return j < 4 ? OFF_OA + j * O_BYTES : j < 6 ? OFF_CH0 + (j - 4) * O_BYTES : OFF_OA + (j - 6) * O_BYTES; }
__device__ __forceinline__ uint32_t off_w(int j) { return j < 4 ? OFF_WA + j * WO_BYTES : j == 4 ? OFF_KVX : j == 5 ? OFF_WC : OFF_WA + (j - 6) * WO_BYTES; }
__device__ __forceinline__ int step_src(int hg, int j) { return SRC_ROT ? (hg + j) & 7 : j == 0 ? hg : j <= hg ? j - 1 : j; }
__device__ __forceinline__ bool tail_first(int hg) { return TAILF && (hg & 3) == 3; }
__device__ __forceinline__ uint32_t off_ch(int c) { return (c < 3 ? OFF_CH0 : OFF_CH3 - 3 * CH_BYTES) + c * CH_BYTES; }

#define U_PITCH 264
__device__ __align__(1024) uint4 g_U[DIM * U_PITCH];
__device__ uint4 g_O[NCTA * 1280];
#define g_Y g_U
constexpr int Y_PITCH = U_PITCH;
__device__ uint4 g_WO[64 * 800];
__device__ uint4 g_halo[NCTA * 2 * 7 * 32];
__device__ float g_gate[SEQ + PAD_KB * 256];
__device__ unsigned g_cnt[32 * (1 + 2 * 16 + 8 + NCTA)];
constexpr int C_LAUNCH = 0, C_PREP = 32, C_Y = 32 * 17, C_W = 32 * 33, C_O = 32 * 41;

#define TSM(cond, slot) do { } while (0)
#define TSIF(cond, slot) do { if (__LINE__ >= FENCE_LO && __LINE__ < FENCE_HI) sched_fence(); } while (0)
__device__ __forceinline__ void sched_fence() {
  asm volatile("{\n.reg .pred p;\n.reg .u32 c;\nmov.u32 c, %%clock;\nsetp.eq.u32 p, c, 0;\n@p st.shared.u32 [%0], c;\n}"
               ::"r"(1024 + OFF_EPOCH + 4) : "memory");
}
#define TS(slot) TSIF(true, slot)

struct Params {
  const __nv_bfloat16 *q, *k, *v, *shift_k, *ssm_k, *ssm_D, *wqkv, *wo, *gate_w;
  __nv_bfloat16* out;
  uint32_t zero;
};

#define POLL_NS 0
constexpr int SPIN_LIMIT = 1 << 17;

__device__ __forceinline__ void mbar_init(uint32_t bar, uint32_t count) {
  asm volatile("mbarrier.init.shared::cta.b64 [%0], %1;" ::"r"(bar), "r"(count) : "memory");
}
__device__ __forceinline__ void mbar_expect_tx(uint32_t bar, uint32_t bytes) {
  asm volatile("mbarrier.arrive.expect_tx.shared::cta.b64 _, [%0], %1;" ::"r"(bar), "r"(bytes) : "memory");
}
__device__ __forceinline__ void mbar_arrive(uint32_t bar) {
  asm volatile("mbarrier.arrive.shared::cta.b64 _, [%0];" ::"r"(bar) : "memory");
}
__device__ __forceinline__ void mbar_wait(uint32_t bar, uint32_t parity) {
  uint32_t ok;
  int spins = 0;
  do {
    if (WAIT_NS)
      asm volatile("{\n.reg .pred p;\nmbarrier.try_wait.parity.shared::cta.b64 p, [%1], %2, %3;\nselp.b32 %0, 1, 0, p;\n}"
                   : "=r"(ok) : "r"(bar), "r"(parity), "r"(WAIT_NS) : "memory");
    else
      asm volatile("{\n.reg .pred p;\nmbarrier.try_wait.parity.shared::cta.b64 p, [%1], %2;\nselp.b32 %0, 1, 0, p;\n}"
                   : "=r"(ok) : "r"(bar), "r"(parity) : "memory");
    if (++spins > SPIN_LIMIT) break;
  } while (!ok);
}
__device__ __forceinline__ void flag_poll(const unsigned* p, unsigned target) {
  unsigned v;
  int spins = 0;
  do {
    if (POLL_NS && spins) __nanosleep(POLL_NS);
    asm volatile("ld.relaxed.gpu.global.u32 %0, [%1];" : "=r"(v) : "l"(p) : "memory");
    if (++spins > SPIN_LIMIT) break;
  } while ((int)(v - target) < 0);
}
__device__ __forceinline__ void flag_wait(const unsigned* p, unsigned target) {
  flag_poll(p, target);
  if (ACQ) asm volatile("fence.acquire.gpu;\nfence.proxy.async.global;" ::: "memory");
}
__device__ __forceinline__ void flag_signal(unsigned* p, int n, int lane) {
  if (lane == 0) asm volatile("fence.release.gpu;" ::: "memory");
  __syncwarp();
  if (lane < n) asm volatile("red.relaxed.gpu.global.add.u32 [%0], 1;" ::"l"(p + 32 * lane) : "memory");
}
__device__ __forceinline__ void flag_bump(unsigned* p) {
  asm volatile("red.relaxed.gpu.global.add.u32 [%0], 1;" ::"l"(p) : "memory");
}
__device__ __forceinline__ void fence_async_smem() { asm volatile("fence.proxy.async.shared::cta;" ::: "memory"); }
__device__ __forceinline__ void wg_sync(int id) { asm volatile("bar.sync %0, 128;" ::"r"(id) : "memory"); }

__device__ __forceinline__ void tma_2d(uint32_t dst, const CUtensorMap* tm, int c0, int c1, uint32_t bar) {
  asm volatile("cp.async.bulk.tensor.2d.shared::cluster.global.mbarrier::complete_tx::bytes [%0], [%1, {%3, %4}], [%2];"
               ::"r"(dst), "l"(tm), "r"(bar), "r"(c0), "r"(c1) : "memory");
}
__device__ __forceinline__ void tma_3d(uint32_t dst, const CUtensorMap* tm, int c0, int c1, int c2, uint32_t bar) {
  asm volatile("cp.async.bulk.tensor.3d.shared::cluster.global.mbarrier::complete_tx::bytes [%0], [%1, {%3, %4, %5}], [%2];"
               ::"r"(dst), "l"(tm), "r"(bar), "r"(c0), "r"(c1), "r"(c2) : "memory");
}
__device__ __forceinline__ void bulk_load(uint32_t dst, const void* src, uint32_t bytes, uint32_t bar) {
  asm volatile("cp.async.bulk.shared::cluster.global.mbarrier::complete_tx::bytes [%0], [%1], %2, [%3];"
               ::"r"(dst), "l"(src), "r"(bytes), "r"(bar) : "memory");
}
__device__ __forceinline__ void tm_prefetch(const CUtensorMap* tm) {
  asm volatile("prefetch.tensormap [%0];" ::"l"(tm) : "memory");
}

__device__ __forceinline__ void wg_fence() { asm volatile("wgmma.fence.sync.aligned;" ::: "memory"); }
__device__ __forceinline__ void wg_commit() { asm volatile("wgmma.commit_group.sync.aligned;" ::: "memory"); }
template <int N> __device__ __forceinline__ void wg_wait() { asm volatile("wgmma.wait_group.sync.aligned %0;" ::"n"(N) : "memory"); }
__device__ __forceinline__ uint32_t desc_lo(uint32_t addr, uint32_t lbo) { return ((addr & 0x3FFFF) >> 4) | ((lbo >> 4) << 16); }
constexpr uint32_t desc_hi(uint32_t sbo, uint32_t swz) { return (sbo >> 4) | (swz << 30); }
constexpr uint32_t HI_SW128 = desc_hi(1024, 1), HI_SW64 = desc_hi(512, 2), HI_SW32 = desc_hi(256, 3), HI_NONE = desc_hi(128, 0);
template <int N> __device__ __forceinline__ void pin(float* d) {
#pragma unroll
  for (int i = 0; i < N; i++) asm volatile("" : "+f"(d[i])::"memory");
}

__device__ __forceinline__ uint32_t lds32(uint32_t a) {
  uint32_t v;
  asm volatile("ld.volatile.shared.u32 %0, [%1];" : "=r"(v) : "r"(a) : "memory");
  return v;
}
__device__ __forceinline__ uint4 ldg128(const void* a) {
  uint4 v;
  asm volatile("ld.global.nc.v4.u32 {%0, %1, %2, %3}, [%4];" : "=r"(v.x), "=r"(v.y), "=r"(v.z), "=r"(v.w) : "l"(a) : "memory");
  return v;
}
__device__ __forceinline__ uint2 ldg64(const void* a) {
  uint2 v;
  asm volatile("ld.global.nc.v2.u32 {%0, %1}, [%2];" : "=r"(v.x), "=r"(v.y) : "l"(a) : "memory");
  return v;
}
__device__ __forceinline__ void ldsm4(uint32_t* r, uint32_t a) {
  asm volatile("ldmatrix.sync.aligned.m8n8.x4.shared.b16 {%0, %1, %2, %3}, [%4];"
               : "=r"(r[0]), "=r"(r[1]), "=r"(r[2]), "=r"(r[3]) : "r"(a) : "memory");
}
__device__ __forceinline__ void ldsm4t(uint32_t* r, uint32_t a) {
  asm volatile("ldmatrix.sync.aligned.m8n8.x4.trans.shared.b16 {%0, %1, %2, %3}, [%4];"
               : "=r"(r[0]), "=r"(r[1]), "=r"(r[2]), "=r"(r[3]) : "r"(a) : "memory");
}
__device__ __forceinline__ uint4 lds128(uint32_t a) {
  uint4 v;
  asm volatile("ld.shared.v4.u32 {%0, %1, %2, %3}, [%4];" : "=r"(v.x), "=r"(v.y), "=r"(v.z), "=r"(v.w) : "r"(a) : "memory");
  return v;
}
__device__ __forceinline__ void sts128(uint32_t a, uint32_t x, uint32_t y, uint32_t z, uint32_t w) {
  asm volatile("st.shared.v4.u32 [%0], {%1, %2, %3, %4};" ::"r"(a), "r"(x), "r"(y), "r"(z), "r"(w) : "memory");
}
__device__ __forceinline__ void stsm4(uint32_t a, const uint32_t* r) {
  asm volatile("stmatrix.sync.aligned.m8n8.x4.shared.b16 [%0], {%1, %2, %3, %4};" ::"r"(a), "r"(r[0]), "r"(r[1]), "r"(r[2]), "r"(r[3]) : "memory");
}
__device__ __forceinline__ void stsm4t(uint32_t a, const uint32_t* r) {
  asm volatile("stmatrix.sync.aligned.m8n8.x4.trans.shared.b16 [%0], {%1, %2, %3, %4};" ::"r"(a), "r"(r[0]), "r"(r[1]), "r"(r[2]), "r"(r[3]) : "memory");
}
__device__ __forceinline__ uint32_t pack2(float lo, float hi) {
  uint32_t r;
  asm("cvt.rn.bf16x2.f32 %0, %1, %2;" : "=r"(r) : "f"(hi), "f"(lo));
  return r;
}
__device__ __forceinline__ uint32_t movm(uint32_t a) {
  uint32_t d;
  asm volatile("movmatrix.sync.aligned.m8n8.trans.b16 %0, %1;" : "=r"(d) : "r"(a));
  return d;
}
__device__ __forceinline__ uint32_t bmul(uint32_t a, uint32_t b) {
  uint32_t d;
  asm("mul.rn.bf16x2 %0, %1, %2;" : "=r"(d) : "r"(a), "r"(b));
  return d;
}
__device__ __forceinline__ uint32_t badd(uint32_t a, uint32_t b) {
  uint32_t d;
  asm("add.rn.bf16x2 %0, %1, %2;" : "=r"(d) : "r"(a), "r"(b));
  return d;
}
__device__ __forceinline__ float bf_lo(uint32_t x) { return __uint_as_float(x << 16); }
__device__ __forceinline__ float bf_hi(uint32_t x) { return __uint_as_float(x & 0xFFFF0000u); }
__device__ __forceinline__ float ex2(float x) {
  float y;
  asm("ex2.approx.ftz.f32 %0, %1;" : "=f"(y) : "f"(x));
  return y;
}
__device__ __forceinline__ float rcp(float x) {
  float y;
  asm("rcp.approx.ftz.f32 %0, %1;" : "=f"(y) : "f"(x));
  return y;
}
__device__ __forceinline__ void mma16816(float* d, uint32_t a0, uint32_t a1, uint32_t a2, uint32_t a3, uint32_t b0, uint32_t b1) {
  asm volatile("mma.sync.aligned.m16n8k16.row.col.f32.bf16.bf16.f32 {%0, %1, %2, %3}, {%4, %5, %6, %7}, {%8, %9}, {%0, %1, %2, %3};"
               : "+f"(d[0]), "+f"(d[1]), "+f"(d[2]), "+f"(d[3])
               : "r"(a0), "r"(a1), "r"(a2), "r"(a3), "r"(b0), "r"(b1));
}
__device__ __forceinline__ void mma1688(float* d, uint32_t a0, uint32_t a1, uint32_t b0) {
  asm volatile("mma.sync.aligned.m16n8k8.row.col.f32.bf16.bf16.f32 {%0, %1, %2, %3}, {%4, %5}, {%6}, {%0, %1, %2, %3};"
               : "+f"(d[0]), "+f"(d[1]), "+f"(d[2]), "+f"(d[3])
               : "r"(a0), "r"(a1), "r"(b0));
}

template <int N> struct WgRS;
template <int N> struct WgSST;
template <> struct WgRS<32> {
  template <uint32_t HB>
  static __device__ __forceinline__ void mma(float* d, const uint32_t* a, uint32_t db) {
    asm volatile("{\n.reg .pred p;\n.reg .b64 db;\nsetp.ne.b32 p, %22, 0;\n"
      "mov.b64 db, {%20, %21};\n"
      "wgmma.mma_async.sync.aligned.m64n32k16.f32.bf16.bf16 {"
      "%0, %1, %2, %3, %4, %5, %6, %7, %8, %9, %10, %11, %12, %13, %14, %15"
      "}, {%16, %17, %18, %19}, db, p, 1, 1, 1;\n}\n"
      : "+f"(d[0]), "+f"(d[1]), "+f"(d[2]), "+f"(d[3]), "+f"(d[4]), "+f"(d[5]), "+f"(d[6]), "+f"(d[7]),
        "+f"(d[8]), "+f"(d[9]), "+f"(d[10]), "+f"(d[11]), "+f"(d[12]), "+f"(d[13]), "+f"(d[14]), "+f"(d[15])
      : "r"(a[0]), "r"(a[1]), "r"(a[2]), "r"(a[3]), "r"(db), "n"(HB), "n"(1));
  }
  template <uint32_t HB>
  static __device__ __forceinline__ void set(float* d, const uint32_t* a, uint32_t db) {
    asm volatile("{\n.reg .pred p;\n.reg .b64 db;\nsetp.ne.b32 p, %22, 0;\n"
      "mov.b64 db, {%20, %21};\n"
      "wgmma.mma_async.sync.aligned.m64n32k16.f32.bf16.bf16 {"
      "%0, %1, %2, %3, %4, %5, %6, %7, %8, %9, %10, %11, %12, %13, %14, %15"
      "}, {%16, %17, %18, %19}, db, p, 1, 1, 1;\n}\n"
      : "=f"(d[0]), "=f"(d[1]), "=f"(d[2]), "=f"(d[3]), "=f"(d[4]), "=f"(d[5]), "=f"(d[6]), "=f"(d[7]),
        "=f"(d[8]), "=f"(d[9]), "=f"(d[10]), "=f"(d[11]), "=f"(d[12]), "=f"(d[13]), "=f"(d[14]), "=f"(d[15])
      : "r"(a[0]), "r"(a[1]), "r"(a[2]), "r"(a[3]), "r"(db), "n"(HB), "n"(0));
  }
};
template <> struct WgRS<64> {
  template <uint32_t HB>
  static __device__ __forceinline__ void mma(float* d, const uint32_t* a, uint32_t db) {
    asm volatile("{\n.reg .pred p;\n.reg .b64 db;\nsetp.ne.b32 p, %38, 0;\n"
      "mov.b64 db, {%36, %37};\n"
      "wgmma.mma_async.sync.aligned.m64n64k16.f32.bf16.bf16 {"
      "%0, %1, %2, %3, %4, %5, %6, %7, %8, %9, %10, %11, %12, %13, %14, %15, "
      "%16, %17, %18, %19, %20, %21, %22, %23, %24, %25, %26, %27, %28, %29, %30, %31"
      "}, {%32, %33, %34, %35}, db, p, 1, 1, 1;\n}\n"
      : "+f"(d[0]), "+f"(d[1]), "+f"(d[2]), "+f"(d[3]), "+f"(d[4]), "+f"(d[5]), "+f"(d[6]), "+f"(d[7]),
        "+f"(d[8]), "+f"(d[9]), "+f"(d[10]), "+f"(d[11]), "+f"(d[12]), "+f"(d[13]), "+f"(d[14]), "+f"(d[15]),
        "+f"(d[16]), "+f"(d[17]), "+f"(d[18]), "+f"(d[19]), "+f"(d[20]), "+f"(d[21]), "+f"(d[22]), "+f"(d[23]),
        "+f"(d[24]), "+f"(d[25]), "+f"(d[26]), "+f"(d[27]), "+f"(d[28]), "+f"(d[29]), "+f"(d[30]), "+f"(d[31])
      : "r"(a[0]), "r"(a[1]), "r"(a[2]), "r"(a[3]), "r"(db), "n"(HB), "n"(1));
  }
  template <uint32_t HB>
  static __device__ __forceinline__ void set(float* d, const uint32_t* a, uint32_t db) {
    asm volatile("{\n.reg .pred p;\n.reg .b64 db;\nsetp.ne.b32 p, %38, 0;\n"
      "mov.b64 db, {%36, %37};\n"
      "wgmma.mma_async.sync.aligned.m64n64k16.f32.bf16.bf16 {"
      "%0, %1, %2, %3, %4, %5, %6, %7, %8, %9, %10, %11, %12, %13, %14, %15, "
      "%16, %17, %18, %19, %20, %21, %22, %23, %24, %25, %26, %27, %28, %29, %30, %31"
      "}, {%32, %33, %34, %35}, db, p, 1, 1, 1;\n}\n"
      : "=f"(d[0]), "=f"(d[1]), "=f"(d[2]), "=f"(d[3]), "=f"(d[4]), "=f"(d[5]), "=f"(d[6]), "=f"(d[7]),
        "=f"(d[8]), "=f"(d[9]), "=f"(d[10]), "=f"(d[11]), "=f"(d[12]), "=f"(d[13]), "=f"(d[14]), "=f"(d[15]),
        "=f"(d[16]), "=f"(d[17]), "=f"(d[18]), "=f"(d[19]), "=f"(d[20]), "=f"(d[21]), "=f"(d[22]), "=f"(d[23]),
        "=f"(d[24]), "=f"(d[25]), "=f"(d[26]), "=f"(d[27]), "=f"(d[28]), "=f"(d[29]), "=f"(d[30]), "=f"(d[31])
      : "r"(a[0]), "r"(a[1]), "r"(a[2]), "r"(a[3]), "r"(db), "n"(HB), "n"(0));
  }
};
template <> struct WgSST<48> {
  template <uint32_t HA, uint32_t HB>
  static __device__ __forceinline__ void mma(float* d, uint32_t da, uint32_t db, int sc) {
    asm volatile("{\n.reg .pred p;\n.reg .b64 da, db;\nsetp.ne.b32 p, %28, 0;\n"
      "mov.b64 da, {%24, %25};\nmov.b64 db, {%26, %27};\n"
      "wgmma.mma_async.sync.aligned.m64n48k16.f32.bf16.bf16 {"
      "%0, %1, %2, %3, %4, %5, %6, %7, %8, %9, %10, %11, %12, %13, %14, %15, "
      "%16, %17, %18, %19, %20, %21, %22, %23"
      "}, da, db, p, 1, 1, 0, 1;\n}\n"
      : "+f"(d[0]), "+f"(d[1]), "+f"(d[2]), "+f"(d[3]), "+f"(d[4]), "+f"(d[5]), "+f"(d[6]), "+f"(d[7]),
        "+f"(d[8]), "+f"(d[9]), "+f"(d[10]), "+f"(d[11]), "+f"(d[12]), "+f"(d[13]), "+f"(d[14]), "+f"(d[15]),
        "+f"(d[16]), "+f"(d[17]), "+f"(d[18]), "+f"(d[19]), "+f"(d[20]), "+f"(d[21]), "+f"(d[22]), "+f"(d[23])
      : "r"(da), "n"(HA), "r"(db), "n"(HB), "r"(sc));
  }
};
template <> struct WgSST<80> {
  template <uint32_t HA, uint32_t HB>
  static __device__ __forceinline__ void mma(float* d, uint32_t da, uint32_t db, int sc) {
    asm volatile("{\n.reg .pred p;\n.reg .b64 da, db;\nsetp.ne.b32 p, %44, 0;\n"
      "mov.b64 da, {%40, %41};\nmov.b64 db, {%42, %43};\n"
      "wgmma.mma_async.sync.aligned.m64n80k16.f32.bf16.bf16 {"
      "%0, %1, %2, %3, %4, %5, %6, %7, %8, %9, %10, %11, %12, %13, %14, %15, "
      "%16, %17, %18, %19, %20, %21, %22, %23, %24, %25, %26, %27, %28, %29, %30, %31, "
      "%32, %33, %34, %35, %36, %37, %38, %39"
      "}, da, db, p, 1, 1, 0, 1;\n}\n"
      : "+f"(d[0]), "+f"(d[1]), "+f"(d[2]), "+f"(d[3]), "+f"(d[4]), "+f"(d[5]), "+f"(d[6]), "+f"(d[7]),
        "+f"(d[8]), "+f"(d[9]), "+f"(d[10]), "+f"(d[11]), "+f"(d[12]), "+f"(d[13]), "+f"(d[14]), "+f"(d[15]),
        "+f"(d[16]), "+f"(d[17]), "+f"(d[18]), "+f"(d[19]), "+f"(d[20]), "+f"(d[21]), "+f"(d[22]), "+f"(d[23]),
        "+f"(d[24]), "+f"(d[25]), "+f"(d[26]), "+f"(d[27]), "+f"(d[28]), "+f"(d[29]), "+f"(d[30]), "+f"(d[31]),
        "+f"(d[32]), "+f"(d[33]), "+f"(d[34]), "+f"(d[35]), "+f"(d[36]), "+f"(d[37]), "+f"(d[38]), "+f"(d[39])
      : "r"(da), "n"(HA), "r"(db), "n"(HB), "r"(sc));
  }
};
template <> struct WgSST<192> {
  template <uint32_t HA, uint32_t HB>
  static __device__ __forceinline__ void mma(float* d, uint32_t da, uint32_t db, int sc) {
    asm volatile("{\n.reg .pred p;\n.reg .b64 da, db;\nsetp.ne.b32 p, %100, 0;\n"
      "mov.b64 da, {%96, %97};\nmov.b64 db, {%98, %99};\n"
      "wgmma.mma_async.sync.aligned.m64n192k16.f32.bf16.bf16 {"
      "%0, %1, %2, %3, %4, %5, %6, %7, %8, %9, %10, %11, %12, %13, %14, %15, "
      "%16, %17, %18, %19, %20, %21, %22, %23, %24, %25, %26, %27, %28, %29, %30, %31, "
      "%32, %33, %34, %35, %36, %37, %38, %39, %40, %41, %42, %43, %44, %45, %46, %47, "
      "%48, %49, %50, %51, %52, %53, %54, %55, %56, %57, %58, %59, %60, %61, %62, %63, "
      "%64, %65, %66, %67, %68, %69, %70, %71, %72, %73, %74, %75, %76, %77, %78, %79, "
      "%80, %81, %82, %83, %84, %85, %86, %87, %88, %89, %90, %91, %92, %93, %94, %95"
      "}, da, db, p, 1, 1, 0, 1;\n}\n"
      : "+f"(d[0]), "+f"(d[1]), "+f"(d[2]), "+f"(d[3]), "+f"(d[4]), "+f"(d[5]), "+f"(d[6]), "+f"(d[7]),
        "+f"(d[8]), "+f"(d[9]), "+f"(d[10]), "+f"(d[11]), "+f"(d[12]), "+f"(d[13]), "+f"(d[14]), "+f"(d[15]),
        "+f"(d[16]), "+f"(d[17]), "+f"(d[18]), "+f"(d[19]), "+f"(d[20]), "+f"(d[21]), "+f"(d[22]), "+f"(d[23]),
        "+f"(d[24]), "+f"(d[25]), "+f"(d[26]), "+f"(d[27]), "+f"(d[28]), "+f"(d[29]), "+f"(d[30]), "+f"(d[31]),
        "+f"(d[32]), "+f"(d[33]), "+f"(d[34]), "+f"(d[35]), "+f"(d[36]), "+f"(d[37]), "+f"(d[38]), "+f"(d[39]),
        "+f"(d[40]), "+f"(d[41]), "+f"(d[42]), "+f"(d[43]), "+f"(d[44]), "+f"(d[45]), "+f"(d[46]), "+f"(d[47]),
        "+f"(d[48]), "+f"(d[49]), "+f"(d[50]), "+f"(d[51]), "+f"(d[52]), "+f"(d[53]), "+f"(d[54]), "+f"(d[55]),
        "+f"(d[56]), "+f"(d[57]), "+f"(d[58]), "+f"(d[59]), "+f"(d[60]), "+f"(d[61]), "+f"(d[62]), "+f"(d[63]),
        "+f"(d[64]), "+f"(d[65]), "+f"(d[66]), "+f"(d[67]), "+f"(d[68]), "+f"(d[69]), "+f"(d[70]), "+f"(d[71]),
        "+f"(d[72]), "+f"(d[73]), "+f"(d[74]), "+f"(d[75]), "+f"(d[76]), "+f"(d[77]), "+f"(d[78]), "+f"(d[79]),
        "+f"(d[80]), "+f"(d[81]), "+f"(d[82]), "+f"(d[83]), "+f"(d[84]), "+f"(d[85]), "+f"(d[86]), "+f"(d[87]),
        "+f"(d[88]), "+f"(d[89]), "+f"(d[90]), "+f"(d[91]), "+f"(d[92]), "+f"(d[93]), "+f"(d[94]), "+f"(d[95])
      : "r"(da), "n"(HA), "r"(db), "n"(HB), "r"(sc));
  }
};

struct FftConst {
  uint32_t f[2][4], fi[4][4];
  float ta[4], tb[4];
};
__device__ __forceinline__ void cis(int m, float scale, float& c, float& s) {
  const float a = (float)m * (-6.283185307179586f * scale);
  c = __cosf(a);
  s = __sinf(a);
}
__device__ __forceinline__ void fft_tables(uint32_t (&v)[12], int tw) {
  const int row = tw >> 2, ch = tw & 3;
#pragma unroll
  for (int i = 0; i < 4; i++) {
    float c[2], s[2], x[2];
#pragma unroll
    for (int e = 0; e < 2; e++) {
      cis((((32 * (8 * ch + 2 * i + e) + 15) * (4 * row - 63) + 2048) & 4095) - 2048, 1.f / 4096, c[e], s[e]);
      float gc, gs;
      cis((((row & 15) * (8 * (ch & 1) + 2 * i + e) + 8) & 15) - 8, 1.f / 16, gc, gs);
      x[e] = (row >> 4) == (ch >> 1) ? gc : (ch >> 1) ? gs : -gs;
    }
    v[i] = pack2(c[0] * 0.125f, c[1] * 0.125f);
    v[4 + i] = pack2(s[0] * 0.125f, s[1] * 0.125f);
    v[8 + i] = pack2(x[0], x[1]);
  }
#pragma unroll
  for (int i = 0; i < 12; i++) asm volatile("" : "+r"(v[i]));
}
__device__ __forceinline__ void fft_tables_store(const uint32_t (&v)[12], uint32_t sb, int tw) {
  const int row = tw >> 2;
  const uint32_t x = ((tw ^ (row >> 1)) & 3) << 4, a = sb + OFF_FT + (16 * (row >> 3) + (row & 7)) * 64 + x;
  sts128(a, v[0], v[1], v[2], v[3]);
  sts128(a + 512, v[4], v[5], v[6], v[7]);
  sts128(sb + OFF_GT + row * 64 + x, v[8], v[9], v[10], v[11]);
}
__device__ __forceinline__ void fft_twiddles(FftConst& k, int w, int lane) {
#pragma unroll
  for (int i = 0; i < 4; i++) {
    float c, s;
    cis((2 * (8 * (i >> 1) + 2 * (lane & 3) + (i & 1)) - 15) * (4 * (8 * w + (lane >> 2)) - 63), 1.f / 4096, c, s);
    k.ta[i] = __fdividef(-s, 1.f + c);
    k.tb[i] = s;
  }
  pin<4>(k.ta);
  pin<4>(k.tb);
}
__device__ __forceinline__ void fft_matrices(FftConst& k, uint32_t sb, int w, int lane) {
  const uint32_t x = (lane >> 1) & 3;
#pragma unroll
  for (int i = 0; i < 2; i++) {
    ldsm4(k.f[i], sb + OFF_FT + (16 * w + (lane & 15)) * 64 + (((2 * i + (lane >> 4)) ^ x) << 4));
    ldsm4t(k.fi[i], sb + OFF_FT + (32 * i + lane) * 64 + ((w ^ x) << 4));
#pragma unroll
    for (int j = 0; j < 4; j++) {
      k.fi[2 + i][j] = (j & 1) ? k.fi[i][j - 1] ^ 0x80008000u : k.fi[i][j + 1];
      asm volatile("" : "+r"(k.fi[2 + i][j]));
    }
  }
}
template <bool INV> __device__ __forceinline__ void rot(float& x, float& y, float a, float b) {
  x = fmaf(INV ? -a : a, y, x);
  y = fmaf(INV ? -b : b, x, y);
  x = fmaf(INV ? -a : a, y, x);
}
__device__ __forceinline__ void twiddle_fwd(uint32_t (&a)[4][4], float* d, const FftConst& k) {
#pragma unroll
  for (int q = 0; q < 4; q++)
#pragma unroll
    for (int j = 0; j < 2; j++) {
      float* x = d + 8 * q + 4 * j;
      rot<false>(x[0], x[2], k.ta[2 * j], k.tb[2 * j]);
      rot<false>(x[1], x[3], k.ta[2 * j + 1], k.tb[2 * j + 1]);
      a[q & 2][2 * j + (q & 1)] = pack2(x[0], x[1]);
      a[(q & 2) + 1][2 * j + (q & 1)] = pack2(x[2], x[3]);
    }
}
__device__ __forceinline__ void g_step(float* d, const uint32_t (&a)[4][4], uint32_t dre, uint32_t dim) {
  WgRS<32>::set<HI_SW64>(d, a[0], dre);
  WgRS<32>::set<HI_SW64>(d + 16, a[2], dre);
  WgRS<32>::mma<HI_SW64>(d, a[1], dim);
  WgRS<32>::mma<HI_SW64>(d + 16, a[3], dim);
  wg_commit();
}

__device__ __forceinline__ void conv_channel(const FftConst& k, uint32_t sb, int c, int wg, int w, int lane) {
  const uint32_t cb = sb + off_ch(c), bars = sb + OFF_BAR;
  const uint32_t du = desc_lo(cb, 1024), dg = desc_lo(sb + OFF_GT, 16), dz = desc_lo(cb + U_BYTES, 16);
  float U[32], H[32];
  uint32_t a[4][4], e[4][4];
  const float dv = __uint_as_float(lds32(sb + OFF_D + 4 * c));
  wg_fence();
  WgRS<64>::set<HI_SW32>(H, k.f[0], du + 256);
  WgRS<64>::mma<HI_SW32>(H, k.f[1], du + 256 + 32);
  wg_commit();
  wg_wait<0>();
  pin<32>(H);
  twiddle_fwd(a, H, k);
  if (ATT_GATE && H_EARLY) mbar_wait(bars + 8 * B_ATTN, 0);
  mbar_wait(bars + 8 * (B_U + (c < 3 ? c : 3)), 0);
  TSM(w == 0 && c < 3, 7 + wg);
  wg_fence();
  WgRS<64>::set<HI_SW32>(U, k.f[0], du);
  WgRS<64>::mma<HI_SW32>(U, k.f[1], du + 32);
  wg_commit();
  g_step(H, a, dg, dg + 64);
  wg_wait<1>();
  pin<32>(U);
  twiddle_fwd(e, U, k);
  wg_fence();
  g_step(U, e, dg, dg + 64);
  wg_wait<0>();
  pin<32>(U);
  pin<32>(H);
#pragma unroll
  for (int j = 0; j < 2; j++) {
    float pr[4][2], pi[4][2];
#pragma unroll
    for (int x = 0; x < 2; x++) {
      H[4 * j + x] += dv;
#pragma unroll
      for (int m = 0; m < 4; m++) {
#pragma unroll
        for (int q = 0; q <= m; q++) {
          const int ih = 16 * (q >> 1) + 2 * (q & 1) + 4 * j + x, iu = 16 * ((m - q) >> 1) + 2 * ((m - q) & 1) + 4 * j + x;
          pr[m][x] = q ? fmaf(H[ih], U[iu], pr[m][x]) : H[ih] * U[iu];
          pi[m][x] = q ? fmaf(H[ih], U[iu + 8], pi[m][x]) : H[ih] * U[iu + 8];
          pr[m][x] = fmaf(-H[ih + 8], U[iu + 8], pr[m][x]);
          pi[m][x] = fmaf(H[ih + 8], U[iu], pi[m][x]);
        }
      }
    }
#pragma unroll
    for (int m = 0; m < 4; m++) {
      a[m & 2][2 * j + (m & 1)] = pack2(pr[m][0], pr[m][1]);
      a[(m & 2) + 1][2 * j + (m & 1)] = pack2(pi[m][0], pi[m][1]);
    }
  }
  wg_fence();
  g_step(U, a, dg + 64, dg);
  const uint32_t za = cb + U_BYTES + (8 * w + (lane & 7)) * 128 + (((lane >> 3) ^ (lane & 7)) << 4);
  const uint32_t ya = cb + (lane >> 4) * 1024 + (8 * w + (lane & 7)) * 32 + ((((lane >> 3) ^ (lane >> 2)) & 1) << 4);
  wg_sync(1 + wg);
  wg_wait<0>();
  pin<32>(U);
  TSIF(w == 0, 80 + c);
#pragma unroll
  for (int p = 0; p < 2; p++) {
#pragma unroll
    for (int i = 0; i < 4; i++) {
      const int j = i & 1;
      float* x = U + 16 * p + 4 * j + (i & 2);
      rot<true>(x[8], x[0], k.ta[2 * j], k.tb[2 * j]);
      rot<true>(x[9], x[1], k.ta[2 * j + 1], k.tb[2 * j + 1]);
      e[p][i] = pack2(x[8], x[9]);
      e[2 + p][i] = pack2(x[0], x[1]);
    }
    stsm4(za ^ (64 * p), e[p]);
    stsm4((za ^ (64 * p)) + 4096, e[2 + p]);
  }
  fence_async_smem();
  wg_sync(1 + wg);
  wg_fence();
  WgRS<64>::set<HI_SW128>(H, k.fi[0], dz);
#pragma unroll
  for (int ks = 1; ks < 4; ks++) WgRS<64>::mma<HI_SW128>(H, k.fi[ks], dz + 128 * ks);
  wg_commit();
  wg_wait<0>();
  pin<32>(H);
  TSIF(w == 0, 88 + c);
#pragma unroll
  for (int j = 0; j < 8; j++)
    a[j >> 2][j & 3] = j < 2 ? pack2(H[4 * j], H[4 * j + 1]) : pack2(H[4 * j] + H[4 * j - 6], H[4 * j + 1] + H[4 * j - 5]);
  stsm4(ya, a[0]);
  stsm4(ya + 2048, a[1]);
  fence_async_smem();
  __syncwarp();
}

__device__ __forceinline__ void prep_slab(uint4* res, const uint2* sw, uint32_t sb, int slab, int w, int lane) {
  const int t = lane & 3, tp = (lane & 7) >> 1, pos = 8 * tp + 2 * (((lane >> 3) + tp) & 3) + (lane & 1);
  const uint32_t base = sb + OFF_KVS + slab * KVS_BYTES + pos * 128;
  uint32_t kk[2][4][4], vv[2][4];
  mbar_wait(sb + OFF_BAR + 8 * (B_KV + slab), 0);
#pragma unroll
  for (int h = 0; h < 2; h++) {
#pragma unroll
    for (int j = 0; j < 4; j++) {
      const uint32_t a = base + 128 * j;
      ldsm4t(kk[h][j], a + (((w + 4 * h) ^ ((a >> 7) & 7)) << 4));
    }
    const uint32_t a = base + KVS_V;
    ldsm4t(vv[h], a + (((w + 4 * h) ^ ((a >> 7) & 7)) << 4));
  }
#pragma unroll
  for (int h = 0; h < 2; h++) {
    uint32_t (&k)[4][4] = kk[h];
    uint32_t (&v)[4] = vv[h];
    const uint32_t w0 = __byte_perm(sw[h].x, 0, 0x1010), w1 = __byte_perm(sw[h].x, 0, 0x3232);
    const uint32_t w2 = __byte_perm(sw[h].y, 0, 0x1010), w3 = __byte_perm(sw[h].y, 0, 0x3232);
#pragma unroll
    for (int m = 0; m < 4; m++)
      v[m] = bmul(badd(badd(badd(bmul(k[0][m], w3), bmul(k[1][m], w2)), bmul(k[2][m], w1)), bmul(k[3][m], w0)), v[m]);
    uint32_t a[4];
#pragma unroll
    for (int m = 0; m < 4; m++) a[m] = (t & 1) ? v[(m + 3) & 3] : v[m];
    res[h] = (t & 2) ? make_uint4(a[2], a[3], a[0], a[1]) : make_uint4(a[0], a[1], a[2], a[3]);
  }
}

__device__ __forceinline__ void prep_gate(const Params& p, int b, int w, int lane) {
  uint2 gw[5], x[4][5];
#pragma unroll
  for (int j = 0; j < 5; j++) gw[j] = ldg64(reinterpret_cast<const uint2*>(p.gate_w) + lane + 32 * j);
#pragma unroll
  for (int i = 0; i < 4; i++)
#pragma unroll
    for (int j = 0; j < 5; j++)
      x[i][j] = ldg64(reinterpret_cast<const uint2*>(p.q) + (16 * b + 4 * w + i) * (DIM / 4) + lane + 32 * j);
  float s[4];
#pragma unroll
  for (int i = 0; i < 4; i++) {
    s[i] = 0.f;
#pragma unroll
    for (int j = 0; j < 5; j++) {
      const uint32_t m0 = bmul(x[i][j].x, gw[j].x), m1 = bmul(x[i][j].y, gw[j].y);
      s[i] += (bf_lo(m0) + bf_hi(m0)) + (bf_lo(m1) + bf_hi(m1));
    }
  }
  const bool h = lane & 16, q = lane & 8;
  const float a = (h ? s[2] : s[0]) + __shfl_xor_sync(0xffffffffu, h ? s[0] : s[2], 16);
  const float c = (h ? s[3] : s[1]) + __shfl_xor_sync(0xffffffffu, h ? s[1] : s[3], 16);
  float z = (q ? c : a) + __shfl_xor_sync(0xffffffffu, q ? a : c, 8);
#pragma unroll
  for (int o = 4; o > 0; o >>= 1) z += __shfl_xor_sync(0xffffffffu, z, o);
  z = bf_lo(pack2(z, 0.f));
  if ((lane & 7) == 0) g_gate[16 * b + 4 * w + (lane >> 3)] = bf_lo(pack2(__fdividef(1.f, 1.f + __expf(-z)), 0.f));
}

__device__ __forceinline__ uint32_t bmax(uint32_t a, uint32_t b) {
  uint32_t d;
  asm("max.bf16x2 %0, %1, %2;" : "=r"(d) : "r"(a), "r"(b));
  return d;
}
__device__ __forceinline__ void softmax_two(const float (&l)[2][2], uint32_t& p0, uint32_t& p1) {
  constexpr float kScale = 0.22360679774997896f, kLog2e = 1.4426950408889634f;
  const uint32_t r0 = pack2(l[0][0], l[1][0]), r1 = pack2(l[0][1], l[1][1]);
  const uint32_t x0 = pack2(bf_lo(r0) * kScale, bf_hi(r0) * kScale), x1 = pack2(bf_lo(r1) * kScale, bf_hi(r1) * kScale);
  uint32_t m = bmax(x0, x1);
  m = bmax(m, __shfl_xor_sync(0xffffffffu, m, 1));
  m = bmax(m, __shfl_xor_sync(0xffffffffu, m, 2));
  const float m0 = bf_lo(m) * kLog2e, m1 = bf_hi(m) * kLog2e;
  p0 = pack2(ex2(bf_lo(x0) * kLog2e - m0), ex2(bf_lo(x1) * kLog2e - m0));
  p1 = pack2(ex2(bf_hi(x0) * kLog2e - m1), ex2(bf_hi(x1) * kLog2e - m1));
}

__device__ __forceinline__ void halo_read(uint32_t (&kpv)[10], uint32_t (&vpv)[10], uint32_t (&tg)[7], const uint4* hp) {
#pragma unroll
  for (int j = 0; j < 7; j++) {
    uint32_t x0, x1, x2;
    asm volatile("ld.relaxed.gpu.global.v4.u32 {%0, %1, %2, %3}, [%4];"
                 : "=r"(x0), "=r"(x1), "=r"(x2), "=r"(tg[j]) : "l"(hp + 32 * j) : "memory");
    if (j < 4) kpv[3 * j] = x0; else vpv[3 * j - 10] = x0;
    if (j < 3) kpv[3 * j + 1] = x1; else vpv[3 * j - 9] = x1;
    if (j < 3) kpv[3 * j + 2] = x2; else if (j < 6) vpv[3 * j - 8] = x2;
  }
}

template <int ROT>
__device__ __forceinline__ void pack_qkv(const float* acc, uint32_t (&qlo)[10], uint32_t (&qhi)[10], uint32_t (&klo)[10],
                                         uint32_t (&khi)[10], uint32_t (&vlo)[10], uint32_t (&vhi)[10]) {
#pragma unroll
  for (int j = 0; j < 10; j++) {
    const int x = (j + ROT) % 10, tq = x < 8 ? x : 16 + x, tk = x < 8 ? 8 + x : 18 + x, tv = x < 8 ? 16 + x : 20 + x;
    khi[j] = pack2(acc[4 * tk + 2], acc[4 * tk + 3]);
    vhi[j] = movm(pack2(acc[4 * tv + 2], acc[4 * tv + 3]));
    qlo[j] = pack2(acc[4 * tq], acc[4 * tq + 1]);
    qhi[j] = pack2(acc[4 * tq + 2], acc[4 * tq + 3]);
    klo[j] = pack2(acc[4 * tk], acc[4 * tk + 1]);
    vlo[j] = pack2(acc[4 * tv], acc[4 * tv + 1]);
    asm volatile("" : "+r"(khi[j]), "+r"(qlo[j]), "+r"(qhi[j]), "+r"(klo[j]), "+r"(vlo[j]));
  }
}

template <int ROT> __device__ __forceinline__ void halo_send(const float* acc, uint4* ho, uint32_t tag) {
#pragma unroll
  for (int j = 0; j < 7; j++) {
    uint32_t x[3];
#pragma unroll
    for (int e = 0; e < 3; e++) {
      const int i = 3 * j + e, y = (i % 10 + ROT) % 10, tk = y < 8 ? 8 + y : 18 + y, tv = y < 8 ? 16 + y : 20 + y;
      x[e] = i < 10 ? pack2(acc[4 * tk + 2], acc[4 * tk + 3]) : i < 20 ? movm(pack2(acc[4 * tv + 2], acc[4 * tv + 3])) : 0u;
    }
    asm volatile("st.relaxed.gpu.global.v4.u32 [%0], {%1, %2, %3, %4};" ::"l"(ho + 32 * j), "r"(x[0]), "r"(x[1]), "r"(x[2]), "r"(tag) : "memory");
  }
}

__device__ __forceinline__ void attention(float* acc, uint32_t sb, int b, int par, int w, int lane, uint32_t tag) {
  const int g = lane >> 2, t = lane & 3;
  uint32_t klo[10], khi[10], vlo[10], vhi[10], qlo[10], qhi[10], kpv[10], vpv[10];
  if (HALO_FIRST && w == 3 && b < NCTA - 8) {
    uint4* ho = g_halo + (b * 2 + par) * 224 + lane;
    if (tail_first(b & 7)) halo_send<8>(acc, ho, tag);
    else halo_send<0>(acc, ho, tag);
    TSIF(par == 0, 76);
    pin<120>(acc);
  }
  if (tail_first(b & 7)) pack_qkv<8>(acc, qlo, qhi, klo, khi, vlo, vhi);
  else pack_qkv<0>(acc, qlo, qhi, klo, khi, vlo, vhi);
  const uint32_t xa = sb + OFF_KVX + (par * 3) * 2560 + lane * 16;
  if (w < 3) {
    sts128(xa + w * 2560, khi[0], khi[1], khi[2], khi[3]);
    sts128(xa + w * 2560 + 512, khi[4], khi[5], khi[6], khi[7]);
    sts128(xa + w * 2560 + 1024, khi[8], khi[9], vhi[0], vhi[1]);
    sts128(xa + w * 2560 + 1536, vhi[2], vhi[3], vhi[4], vhi[5]);
    sts128(xa + w * 2560 + 2048, vhi[6], vhi[7], vhi[8], vhi[9]);
  } else if (!HALO_FIRST && b < NCTA - 8) {
    uint4* ho = g_halo + (b * 2 + par) * 224 + lane;
#pragma unroll
    for (int j = 0; j < 7; j++) {
      const uint32_t x0 = j < 4 ? khi[3 * j] : vhi[3 * j - 10], x1 = j < 3 ? khi[3 * j + 1] : vhi[3 * j - 9];
      const uint32_t x2 = j < 3 ? khi[3 * j + 2] : j < 6 ? vhi[3 * j - 8] : 0u;
      asm volatile("st.relaxed.gpu.global.v4.u32 [%0], {%1, %2, %3, %4};" ::"l"(ho + 32 * j), "r"(x0), "r"(x1), "r"(x2), "r"(tag) : "memory");
    }
  }
  TSIF(par == 0 && w == 1, 64);
  TSIF(par == 0 && w == 3 && !HALO_FIRST, 76);
#pragma unroll
  for (int j = 0; j < 10; j++) vlo[j] = movm(vlo[j]);
  const bool far0 = 2 * t > g, far1 = 2 * t + 1 > g;
  const uint32_t mfar = (far0 ? 0x0000FFFFu : 0u) | (far1 ? 0xFFFF0000u : 0u);
  float slo[4][2], shi[4][2], lg[2][2];
  uint32_t phi[4], plo[4], qml[4], qmh[4];
#pragma unroll
  for (int h = 0; h < 4; h++) {
    const int f = h == 0 ? 0 : h == 1 ? 3 : h == 2 ? 5 : 8, hf = h < 2 ? 2 : 7;
    const bool mine = (h & 1) ? t >= 2 : t < 2;
    qml[h] = mine ? qlo[hf] : 0u;
    qmh[h] = mine ? qhi[hf] : 0u;
    float a[4] = {0.f, 0.f, 0.f, 0.f}, c[4] = {0.f, 0.f, 0.f, 0.f};
    mma16816(a, qlo[f], qhi[f], qlo[f + 1], qhi[f + 1], klo[f], klo[f + 1]);
    mma16816(c, qlo[f], qhi[f], qlo[f + 1], qhi[f + 1], khi[f], khi[f + 1]);
    mma1688(a, qml[h], qmh[h], klo[hf]);
    mma1688(c, qml[h], qmh[h], khi[hf]);
    slo[h][0] = a[0];
    slo[h][1] = a[1];
    shi[h][0] = lg[h & 1][0] = far0 ? a[2] : c[2];
    shi[h][1] = lg[h & 1][1] = far1 ? a[3] : c[3];
    if (!ATT_MERGE && (h & 1)) softmax_two(lg, phi[h - 1], phi[h]);
  }
  TSIF(par == 0 && w == 1, 65);
  wg_sync(1 + par);
  TSIF(par == 0 && w == 1, 66);
  const bool nohist = (w == 0) && (b < 8);
  const uint4* hp = g_halo + ((b - 8) * 2 + par) * 224 + lane;
  uint32_t tg[7];
  if (w > 0) {
    const uint4 v0 = lds128(xa + (w - 1) * 2560), v1 = lds128(xa + (w - 1) * 2560 + 512), v2 = lds128(xa + (w - 1) * 2560 + 1024);
    const uint4 v3 = lds128(xa + (w - 1) * 2560 + 1536), v4 = lds128(xa + (w - 1) * 2560 + 2048);
    kpv[0] = v0.x; kpv[1] = v0.y; kpv[2] = v0.z; kpv[3] = v0.w; kpv[4] = v1.x; kpv[5] = v1.y; kpv[6] = v1.z; kpv[7] = v1.w;
    kpv[8] = v2.x; kpv[9] = v2.y; vpv[0] = v2.z; vpv[1] = v2.w; vpv[2] = v3.x; vpv[3] = v3.y; vpv[4] = v3.z; vpv[5] = v3.w;
    vpv[6] = v4.x; vpv[7] = v4.y; vpv[8] = v4.z; vpv[9] = v4.w;
  } else if (nohist) {
#pragma unroll
    for (int j = 0; j < 10; j++) kpv[j] = vpv[j] = 0u;
  } else {
    TSIF(par == 0, 77);
    halo_read(kpv, vpv, tg, hp);
  }
  if (w == 0 && !nohist) {
    int spins = 0;
    while (true) {
      bool ok = true;
#pragma unroll
      for (int j = 0; j < 7; j++) ok = ok && tg[j] == tag;
      if (__all_sync(0xffffffffu, ok) || ++spins > SPIN_LIMIT) break;
      halo_read(kpv, vpv, tg, hp);
    }
    TSIF(par == 0, 79);
  }
#pragma unroll
  for (int h = 0; h < 4; h++) {
    const int f = h == 0 ? 0 : h == 1 ? 3 : h == 2 ? 5 : 8, hf = h < 2 ? 2 : 7;
    float a[4] = {0.f, 0.f, 0.f, 0.f};
    mma16816(a, qlo[f], qhi[f], qlo[f + 1], qhi[f + 1], kpv[f], kpv[f + 1]);
    mma1688(a, qml[h], qmh[h], kpv[hf]);
    const float ninf = __int_as_float(0xff800000);
    lg[h & 1][0] = far0 ? (nohist ? ninf : a[0]) : slo[h][0];
    lg[h & 1][1] = far1 ? (nohist ? ninf : a[1]) : slo[h][1];
    if (h & 1) {
      softmax_two(lg, plo[h - 1], plo[h]);
      if (ATT_MERGE) {
        const float lh[2][2] = {{shi[h - 1][0], shi[h - 1][1]}, {shi[h][0], shi[h][1]}};
        softmax_two(lh, phi[h - 1], phi[h]);
      }
    }
  }
  TSIF(par == 0 && w <= 1, 67 + w);
  uint32_t ov[20];
#pragma unroll
  for (int hp = 0; hp < 2; hp++) {
    const int hf = hp ? 7 : 2;
    float sh[4] = {0.f, 0.f, 0.f, 0.f}, i0 = 0.f, i1 = 0.f;
#pragma unroll
    for (int e = 0; e < 2; e++) {
      const int h = 2 * hp + e, f = h == 0 ? 0 : h == 1 ? 3 : h == 2 ? 5 : 8;
      const uint32_t a0 = plo[h] & mfar, a2 = plo[h] & ~mfar, a3 = phi[h] & mfar, c1 = phi[h] & ~mfar;
      float sum[4] = {0.f, 0.f, 0.f, 0.f};
      mma1688(sum, plo[h], phi[h], 0x3F803F80u);
      const float r0 = rcp(sum[0]), r1 = rcp(sum[2]);
#pragma unroll
      for (int j = f; j < f + 2; j++) {
        float o[4] = {0.f, 0.f, 0.f, 0.f};
        mma16816(o, a0, 0u, a2, a3, vpv[j], vlo[j]);
        mma1688(o, 0u, c1, vhi[j]);
        ov[2 * j] = pack2(o[0] * r0, o[1] * r0);
        ov[2 * j + 1] = pack2(o[2] * r1, o[3] * r1);
      }
      const bool mine = e ? g >= 4 : g < 4;
      mma16816(sh, a0, 0u, a2, a3, mine ? vpv[hf] : 0u, mine ? vlo[hf] : 0u);
      mma1688(sh, 0u, c1, mine ? vhi[hf] : 0u);
      if (e == 0 || t >= 2) {
        i0 = r0;
        i1 = r1;
      }
    }
    ov[2 * hf] = pack2(sh[0] * i0, sh[1] * i0);
    ov[2 * hf + 1] = pack2(sh[2] * i1, sh[3] * i1);
  }
  TS(32 + 4 * par + w);
  mbar_wait(sb + OFF_BAR + 8 * B_P1, 0);
  const uint32_t oa = sb + OFF_OA + (lane >> 4) * 2048 + (32 * w + 2 * (lane & 15) + par) * 16;
#pragma unroll
  for (int j = 0; j < 5; j++) stsm4(oa + 4096 * j, ov + 4 * j);
  TSIF(par == 0 && w == 0, 120);
  fence_async_smem();
  TSIF(par == 0 && w == 0, 121);
  __syncwarp();
  if (lane == 0) mbar_arrive(sb + OFF_BAR + 8 * B_ATTN);
  TSM(w == 0 || w == 2, 122 + par + (w == 2 ? 3 : 0));
}

struct Maps {
  CUtensorMap x, wm, wt, k, v, y, wo, qm, qt, om, ot, u;
};

__device__ __forceinline__ void load_stage(uint32_t sb, int kb, int b, const Maps& m) {
  const uint32_t st = sb + (kb & 3) * STAGE_BYTES, bar = sb + OFF_BAR + 8 * (B_FULL1 + (kb & 3));
  const int r = b >> 3, hg = b & 7, slab = kb - KV_KB;
  const bool kv = slab >= 0 && slab < 5;
  const uint32_t kbar = sb + OFF_BAR + 8 * (B_KV + slab), dst = sb + OFF_KVS + slab * KVS_BYTES;
  mbar_expect_tx(bar, STAGE_BYTES);
  if (kv) mbar_expect_tx(kbar, KVS_BYTES);
  tma_3d(st, &m.x, 64 * kb, 64 * r, 0, bar);
  if (kv && KV_MIX) tma_3d(dst, &m.k, 0, 32 * (b >> 1) - 3, 2 * slab + (b & 1), kbar);
  tma_3d(st + ST_W, &m.wm, 80 * hg + (tail_first(hg) ? 16 : 0), 64 * kb, 0, bar);
  if (kv && KV_MIX) tma_3d(dst + KVS_V, &m.v, 0, 32 * (b >> 1), 2 * slab + (b & 1), kbar);
  tma_3d(st + ST_WT, &m.wt, 80 * hg + (tail_first(hg) ? 0 : 64), 64 * kb, 0, bar);
  if (kv && !KV_MIX) tma_3d(dst, &m.k, 0, 32 * (b >> 1) - 3, 2 * slab + (b & 1), kbar);
  if (kv && !KV_MIX) tma_3d(dst + KVS_V, &m.v, 0, 32 * (b >> 1), 2 * slab + (b & 1), kbar);
}

__global__ void __launch_bounds__(NTHR, 1) fused_kernel(const __grid_constant__ Maps m, const Params p) {
  extern __shared__ __align__(1024) uint8_t smem[];
  const uint32_t sb = (uint32_t)__cvta_generic_to_shared(smem);
  const uint32_t bars = sb + OFF_BAR;
  const int tid = threadIdx.x, lane = tid & 31;
  int b = blockIdx.x;
  if (BMAP == 1) b = (((b & 63) >> 3) * 2 + (b & 1)) * 8 + (((b < 64 ? 0x6521 : 0x7430) >> (4 * ((b >> 1) & 3))) & 7);
  if (BMAP == 2) b = ((b & 63) >> 2) * 8 + (((b < 64 ? 0x6521 : 0x7430) >> (4 * (b & 3))) & 7);
  if (BMAP == 3) b = (((b & 63) >> 3) * 2 + (b & 1)) * 8 + (((b < 64 ? 0x7430 : 0x6521) >> (4 * ((b >> 1) & 3))) & 7);
  if (BMAP == 4) b = (((b >> 4) * 2 + (b & 1)) * 8) + ((b >> 1) & 7);
  if (BMAP == 5) b = 127 - b;
  const int r = b >> 3, hg = b & 7;

  if (tid == T_ISSUE) {
    TSM(true, 0);
#pragma unroll
    for (int i = 0; i < 4; i++) mbar_init(bars + 8 * (B_FULL1 + i), 1);
#pragma unroll
    for (int i = 0; i < 3; i++) mbar_init(bars + 8 * (B_KV + i), 1);
    fence_async_smem();
#pragma unroll 1
    for (int kb = 0; kb <= PRE2; kb++) load_stage(sb, kb, b, m);
  } else if (tid >= T_PF && tid < T_PF + 12) {
    tm_prefetch(&m.x + (tid - T_PF));
  } else if (tid == T_INIT) {
#pragma unroll
    for (int i = 0; i < 4; i++) mbar_init(bars + 8 * (B_EMPTY1 + i), 8);
#pragma unroll
    for (int i = 0; i < 8; i++) mbar_init(bars + 8 * (B_FULL2 + i), 1);
#pragma unroll
    for (int i = 0; i < 4; i++) mbar_init(bars + 8 * (B_EMPTY2 + i), 8);
#pragma unroll
    for (int i = 0; i < 4; i++) mbar_init(bars + 8 * (B_U + i), 1);
    mbar_init(bars + 8 * B_HA, 4);
    mbar_init(bars + 8 * B_GATE, 4);
    mbar_init(bars + 8 * B_HB, 1);
    mbar_init(bars + 8 * B_KVD, 4);
    mbar_init(bars + 8 * B_QF, 1);
    mbar_init(bars + 8 * B_ATTN, 8);
    mbar_init(bars + 8 * B_P1, 8);
    mbar_init(bars + 8 * B_C34, 1);
#pragma unroll
    for (int i = 0; i < 5; i++) mbar_init(bars + 8 * (B_YST + i), 4);
#pragma unroll
    for (int i = 0; i < 5; i++) mbar_init(bars + 8 * (B_US + i), 4);
    mbar_init(bars + 8 * B_YSIG, 1);
    mbar_init(bars + 8 * B_YFULL, 1);
    mbar_init(bars + 8 * B_EPOCH, 1);
    mbar_init(bars + 8 * B_PREP, 4);
    mbar_init(bars + 8 * B_USIG, 1);
    mbar_init(bars + 8 * B_WST, 1);
#pragma unroll
    for (int i = 3; i < 5; i++) mbar_init(bars + 8 * (B_KV + i), 1);
    mbar_init(bars + 8 * B_E3, 8);
    mbar_init(bars + 8 * B_LAST, 1);
    mbar_init(bars + 8 * B_OSIG, 1);
    mbar_init(bars + 8 * B_WOP, 1);
    fence_async_smem();
  }
  const int warp = __shfl_sync(0xffffffffu, tid >> 5, 0), wg = warp >> 2, w = warp & 3;
  __syncthreads();

  if (wg == 3) {
    asm volatile("setmaxnreg.dec.sync.aligned.u32 56;");
    if (w == 0) {
      if (lane == 0) {
#pragma unroll 1
        for (int kb = 1 + PRE2; kb < 10; kb++) {
          if (kb >= 4) mbar_wait(bars + 8 * (kb == 7 ? B_E3 : B_EMPTY1 + (kb & 3)), (kb >> 3) & 1);
          TSIF(kb >= 4, 44 + kb);
          load_stage(sb, kb, b, m);
          TSIF(kb == 3, 60);
          if (kb == TRIG_KB) mbar_arrive(bars + 8 * B_LAST);
        }
        mbar_wait(bars + 8 * B_WOP, 0);
        mbar_wait(bars + 8 * WL_TRIG, 0);
        mbar_wait(bars + 8 * B_EPOCH, 0);
        flag_wait(g_cnt + C_W + 32 * hg, (lds32(sb + OFF_EPOCH) + 1) * 16);
        TS(30);
#pragma unroll 1
        for (int j = 0; j < 8; j++) {
          if (j >= 6) mbar_wait(bars + 8 * (B_EMPTY2 + j - 6), 0);
          if (j == 4) mbar_wait(bars + 8 * B_ATTN, 0);
          TSIF(j >= 6, 100 + j);
          if (RF_GATE && j == 6) mbar_wait(bars + 8 * B_YSIG, 0);
          mbar_expect_tx(bars + 8 * (B_FULL2 + j), j == 0 ? WO_BYTES : j == 5 ? O_BYTES + WO_BYTES + 512 : O_BYTES + WO_BYTES);
          bulk_load(sb + off_w(j), g_WO + (hg * 8 + step_src(hg, j)) * 800, WO_BYTES, bars + 8 * (B_FULL2 + j));
        }
        mbar_wait(bars + 8 * (B_EMPTY2 + 3), 0);
        mbar_expect_tx(bars + 8 * B_QF, O_BYTES);
        tma_2d(sb + OFF_QS, &m.qm, 80 * hg, 128 * r, bars + 8 * B_QF);
        tma_2d(sb + OFF_QT, &m.qt, 80 * hg + 64, 128 * r, bars + 8 * B_QF);
      }
    } else if (w == 1) {
      unsigned epoch = 0;
      if (lane == 0) {
        epoch = atomicAdd(g_cnt + C_LAUNCH, 1u) / NCTA;
        asm volatile("st.shared.u32 [%0], %1;" ::"r"(sb + OFF_EPOCH), "r"(epoch) : "memory");
        mbar_arrive(bars + 8 * B_EPOCH);
        mbar_wait(bars + 8 * B_KVD, 0);
        mbar_expect_tx(bars + 8 * B_HB, 5 * 4096);
#pragma unroll 1
        for (int c = 0; c < 5; c++) {
          if (c == 3) mbar_wait(bars + 8 * B_S3, 0);
          bulk_load(sb + off_ch(c) + U_BYTES, p.ssm_k + (5 * b + c) * SEQ, 4096, bars + 8 * B_HB);
        }
#pragma unroll
        for (int c = 0; c < 4; c++) mbar_expect_tx(bars + 8 * (B_U + c), c < 3 ? U_BYTES : 2 * U_BYTES);
        const uint4* usrc = g_U + 5 * b * U_PITCH;
        mbar_wait(bars + 8 * B_USIG, 0);
        flag_wait(g_cnt + C_PREP + 32 * (b & 15), (epoch + 1) * NCTA);
        TS(23);
#pragma unroll
        for (int c = 0; c < 5; c++) {
          if (c == 3) mbar_wait(bars + 8 * (B_U + 2), 0);
          bulk_load(sb + off_ch(c), usrc + c * U_PITCH, U_BYTES, bars + 8 * (B_U + (c < 3 ? c : 3)));
          TSIF(c == 0 || c == 4, 116 + (c >> 2));
        }
      }
      epoch = __shfl_sync(0xffffffffu, epoch, 0);
      if (lane < 8) {
        const int src = (b & ~7) | step_src(hg, lane);
        mbar_wait(bars + 8 * B_OSIG, 0);
        TS(20);
        flag_wait(g_cnt + C_O + 32 * src, epoch + 1);
        if (lane >= 1 && lane < 4) bulk_load(sb + off_o(lane), g_O + src * 1280, O_BYTES, bars + 8 * (B_FULL2 + lane));
        __syncwarp(0xff);
        TS(21);
        if (lane == 5) bulk_load(sb + OFF_GATE, g_gate + 128 * r, 512, bars + 8 * (B_FULL2 + 5));
#pragma unroll 1
        for (int j = 4; j < 8; j++) {
          if (lane == j) {
            mbar_wait(bars + 8 * (j < 6 ? B_C34 : B_EMPTY2 + j - 6), 0);
            if (RF_GATE && j == 6) mbar_wait(bars + 8 * B_YSIG, 0);
            bulk_load(sb + off_o(j), g_O + src * 1280, O_BYTES, bars + 8 * (B_FULL2 + j));
          }
          __syncwarp(0xff);
        }
        TS(22);
      }
    } else if (w == 2) {
      mbar_wait(bars + 8 * B_PREP, 0);
      flag_signal(g_cnt + C_PREP, 16, lane);
      TS(25);
      if (lane == 0) mbar_arrive(bars + 8 * B_USIG);
      mbar_wait(bars + 8 * B_GATE, 0);
      if ((NOMB & 1) && lane == 0) asm volatile("fence.release.gpu;" ::: "memory");
      mbar_wait(bars + 8 * B_ATTN, 0);
      if (lane == 0) {
        if (O_DEFER) mbar_wait(bars + 8 * (B_U + 3), 0);
        asm volatile("cp.async.bulk.global.shared::cta.bulk_group [%0], [%1], 20480;\ncp.async.bulk.commit_group;\n"
                     "cp.async.bulk.wait_group 0;\nfence.proxy.async.global;" ::"l"(g_O + b * 1280), "r"(sb + OFF_OA) : "memory");
      }
      TS(74);
      if (!(NOMB & 1)) flag_signal(g_cnt + C_O + 32 * b, 1, lane);
      else if (lane == 0) flag_bump(g_cnt + C_O + 32 * b);
      TS(26);
      if (lane == 0) mbar_arrive(bars + 8 * B_OSIG);

    } else {
      if (lane == 0) {
        uint4* dst = g_WO + (hg * 8 + (r >> 1)) * 800 + (r & 1) * 80;
        mbar_wait(bars + 8 * B_P1, 0);
        mbar_wait(bars + 8 * WB_TRIG, 0);
        mbar_expect_tx(bars + 8 * B_WST, WO_BYTES / 2);
        tma_3d(sb + OFF_WS, &m.wo, 0, 40 * r, 5 * hg, bars + 8 * B_WST);
        mbar_wait(bars + 8 * B_WST, 0);
        mbar_wait(bars + 8 * WO_TRIG, 0);
#pragma unroll 1
        for (int n = 0; n < 5; n++)
          asm volatile("cp.async.bulk.global.shared::cta.bulk_group [%0], [%1], 1280;" ::"l"(dst + 160 * n), "r"(sb + OFF_WS + 1280 * n) : "memory");
        asm volatile("cp.async.bulk.commit_group;\ncp.async.bulk.wait_group 0;\nfence.proxy.async.global;" ::: "memory");
        if (!(NOMB & 4)) asm volatile("fence.release.gpu;" ::: "memory");
        flag_bump(g_cnt + C_W + 32 * hg);
        mbar_arrive(bars + 8 * B_WOP);
        TS(71);
#pragma unroll 1
        for (int c = 0; c < 5; c++) {
          mbar_wait(bars + 8 * (B_YST + c), 0);
          asm volatile("cp.async.bulk.global.shared::cta.bulk_group [%0], [%1], 4096;\ncp.async.bulk.commit_group;"
                       ::"l"(g_Y + (5 * b + c) * Y_PITCH), "r"(sb + off_ch(c)) : "memory");
          if (c == 2) {
            asm volatile("cp.async.bulk.wait_group.read 0;" ::: "memory");
            mbar_arrive(bars + 8 * B_C34);
          }
        }
        asm volatile("cp.async.bulk.wait_group 0;\nfence.proxy.async.global;" ::: "memory");
        TS(75);
        if (!(NOMB & 2)) asm volatile("fence.release.gpu;" ::: "memory");
        flag_bump(g_cnt + C_Y + 32 * (b >> 4));
        TS(27);
        mbar_arrive(bars + 8 * B_YSIG);
        mbar_expect_tx(bars + 8 * B_YFULL, 20480);
        flag_wait(g_cnt + C_Y + 32 * hg, (lds32(sb + OFF_EPOCH) + 1) * 16);
        TS(24);
        tma_2d(sb + OFF_YT, &m.y, 128 * r, 80 * hg, bars + 8 * B_YFULL);
        tma_2d(sb + OFF_YT + 10240, &m.y, 128 * r + 64, 80 * hg, bars + 8 * B_YFULL);
      }
    }
  } else {
    asm volatile("setmaxnreg.inc.sync.aligned.u32 152;");
    if (wg < 2) {
      float acc[120];
#pragma unroll
      for (int i = 0; i < 120; i++) acc[i] = 0.f;
      const uint32_t da = desc_lo(sb + wg * 8192, 16), db = desc_lo(sb + ST_W, 8192), dc = desc_lo(sb + ST_WT, 2048);
      if (PW1) pin<120>(acc);
      if (PW1 == 2) mbar_wait(bars + 8 * B_FULL1, 0);
#pragma unroll 1
      for (int kb = 0; kb < 10; kb++) {
        mbar_wait(bars + 8 * (B_FULL1 + (kb & 3)), (kb >> 2) & 1);
        const uint32_t so = (kb & 3) * (STAGE_BYTES >> 4);
        wg_fence();
#pragma unroll
        for (int k = 0; k < 4; k++) {
          WgSST<192>::mma<HI_SW128, HI_SW128>(acc, da + so + 2 * k, db + so + 128 * k, 1);
          WgSST<48>::mma<HI_SW128, HI_SW32>(acc + 96, da + so + 2 * k, dc + so + 32 * k, 1);
        }
        wg_commit();
        wg_wait<1>();
        if (kb > 0 && lane == 0) mbar_arrive(bars + 8 * (kb == 4 ? B_E3 : B_EMPTY1 + ((kb - 1) & 3)));
      }
      mbar_wait(bars + 8 * B_EPOCH, 0);
      const uint32_t tag = lds32(sb + OFF_EPOCH) + 1;
      mbar_wait(bars + 8 * B_S3, 0);
      wg_wait<0>();
      pin<120>(acc);
      if (lane == 0) mbar_arrive(bars + 8 * B_P1);
      TSM(w == 0, 3 + wg);
      attention(acc, sb, b, wg, w, lane, tag);
    } else {
      const int tw = tid & 127, chl = 64 * (b & 1) + 8 * w + (lane >> 2);
      uint4* up = g_U + chl * U_PITCH + ((4 * (b >> 1) + (lane & 3)) ^ ((b >> 2) & 1));
      uint2 sw[10];
      uint32_t dv = 0;
      if (lane < 5) dv = __ldg(reinterpret_cast<const unsigned short*>(p.ssm_D) + 5 * b + lane);
#pragma unroll
      for (int i = 0; i < 10; i++) sw[i] = ldg64(reinterpret_cast<const uint2*>(p.shift_k) + chl + 128 * (i >> 1) + 32 * (i & 1));
      uint32_t tab[12];
      fft_tables(tab, tw);
      uint4 res[10];
#pragma unroll
      for (int i = 0; i < 10; i++) res[i] = make_uint4(0, 0, 0, 0);
#pragma unroll 1
      for (int slab = 0; slab < 5; slab++) {
#pragma unroll
        for (int i = 0; i < 8; i++) res[i] = res[i + 2];
        prep_slab(res + 8, sw, sb, slab, w, lane);
        TSIF(w == 0, 99 + 4 * slab);
#pragma unroll
        for (int i = 0; i < 8; i++) sw[i] = sw[i + 2];
      }
      TSIF(w == 0, 28);
      __syncwarp();
      if (lane == 0) mbar_arrive(bars + 8 * B_KVD + ((res[8].x ^ res[9].x) & p.zero));
      mbar_wait(bars + 8 * B_KVD, 0);
      fft_tables_store(tab, sb, tw);
      mbar_wait(bars + 8 * B_LAST, 0);
#pragma unroll
      for (int i = 0; i < 10; i++) up[(128 * (i >> 1) + 32 * (i & 1)) * U_PITCH] = res[i];
      __syncwarp();
      if (lane == 0) mbar_arrive(bars + 8 * B_PREP);
      TSIF(w == 0 && !U_TMA, 5);
      mbar_wait(bars + 8 * (G_AFTER ? B_USIG : B_LAST), 0);
      prep_gate(p, b, w, lane);
      __syncwarp();
      if (lane == 0) mbar_arrive(bars + 8 * B_GATE);
      TSIF(w == 0, 72);
      mbar_wait(bars + 8 * B_HB, 0);
      TSIF(w == 0, 2);
      const uint32_t ha = sb + U_BYTES + ((tw >> 3) * 16 + 8 + (tw & 7)) * 16;
      uint4 hv[5];
#pragma unroll
      for (int c = 0; c < 5; c++) hv[c] = lds128(ha + off_ch(c));
      __syncwarp();
#pragma unroll
      for (int c = 0; c < 5; c++) sts128((ha ^ 16) + off_ch(c), hv[c].x, hv[c].y, hv[c].z, hv[c].w);
      if (tw < 5) asm volatile("st.shared.f32 [%0], %1;" ::"r"(sb + OFF_D + 4 * tw), "f"(bf_lo(dv) * 0.125f) : "memory");
      fence_async_smem();
      __syncwarp();
      if (lane == 0) mbar_arrive(bars + 8 * B_HA);
      TSIF(w == 0, 6);
    }

    FftConst fc;
    fft_twiddles(fc, w, lane);
    mbar_wait(bars + 8 * B_HA, 0);
    fft_matrices(fc, sb, w, lane);
    if (ATT_GATE && !H_EARLY) mbar_wait(bars + 8 * B_ATTN, 0);
    TSM(w == 0 && wg == 2, 124);
#pragma unroll 1
    for (int c = wg == 2 ? 0 : wg + 1; c < 5; c += !CH_W2 ? 3 : wg < 2 ? 5 : c ? 1 : 3) {
      conv_channel(fc, sb, c, wg, w, lane);
      if (lane == 0) mbar_arrive(bars + 8 * (B_YST + c));
      TSM(w == 0, 10 + c);
    }

    if (wg < 2) {
      const int g = lane >> 2;
      float acc[40];
#pragma unroll
      for (int i = 0; i < 40; i++) acc[i] = 0.f;
      const uint32_t da = desc_lo(sb + wg * 1024, 2048), db = desc_lo(sb, 2560);
      mbar_wait(bars + 8 * B_ATTN, 0);
      mbar_wait(bars + 8 * (B_YST + 3), 0);
      mbar_wait(bars + 8 * (B_YST + 4), 0);
      if (PW2) mbar_wait(bars + 8 * B_FULL2, 0);
      TSM(w == 0, 15 + wg);
#pragma unroll 1
      for (int j = 0; j < 8; j++) {
        mbar_wait(bars + 8 * (B_FULL2 + j), 0);
        const uint32_t oa = da + (off_o(j) >> 4), ob = db + (off_w(j) >> 4);
        wg_fence();
#pragma unroll
        for (int k = 0; k < 5; k++) WgSST<80>::mma<HI_NONE, HI_SW32>(acc, oa + 256 * k, ob + 32 * k, 1);
        wg_commit();
        wg_wait<1>();
        if (j >= 1 && j <= 4 && lane == 0) mbar_arrive(bars + 8 * (B_EMPTY2 + j - 1));
      }
      TSIF(w == 0 && wg == 0, 113);
      const int tr = 64 * wg + 16 * w + (lane & 15);
      const uint32_t fm = sb + OFF_QS + tr * 128, fx = (lane >> 4) ^ (tr & 7);
      const uint32_t ft = sb + OFF_QT + tr * 32 + (((lane >> 4) ^ (tr >> 2)) & 1) * 16;
      const float g0 = __uint_as_float(lds32(sb + OFF_GATE + (64 * wg + 16 * w + g) * 4));
      const float g1 = __uint_as_float(lds32(sb + OFF_GATE + (64 * wg + 16 * w + 8 + g) * 4));
      const uint32_t ga = pack2(g0, g0), gb = pack2(g1, g1);
      const uint32_t na = pack2(1.f - g0, 1.f - g0), nb = pack2(1.f - g1, 1.f - g1);

      wg_wait<0>();
      pin<40>(acc);
      TSM(w == 0, 17 + wg);
      uint32_t pb[20];
#pragma unroll
      for (int j = 0; j < 10; j++) {
        pb[2 * j] = bmul(na, pack2(acc[4 * j], acc[4 * j + 1]));
        pb[2 * j + 1] = bmul(nb, pack2(acc[4 * j + 2], acc[4 * j + 3]));
        asm volatile("" : "+r"(pb[2 * j]), "+r"(pb[2 * j + 1]));
      }
      const uint32_t ya = sb + OFF_YT + wg * 10240 + ((lane >> 4) * 8 + (lane & 7)) * 128 +
                          (((2 * w + (((lane >> 3) & 1) ^ wg)) ^ (lane & 7)) << 4);
      uint32_t qf[20];
      mbar_wait(bars + 8 * B_QF, 0);
#pragma unroll
      for (int j = 0; j < 5; j++) ldsm4(qf + 4 * j, j < 4 ? fm + ((fx ^ (2 * j)) << 4) : ft);
      mbar_wait(bars + 8 * B_YFULL, 0);
      TSM(w == 0 && wg == 0, 19);
#pragma unroll
      for (int j = 0; j < 5; j++) {
        uint32_t y[4];
        ldsm4t(y, ya + 2048 * j);
#pragma unroll
        for (int i = 0; i < 4; i++) qf[4 * j + i] = badd(bmul((i & 1) ? gb : ga, bmul(qf[4 * j + i], y[i])), pb[4 * j + i]);
      }
#pragma unroll
      for (int j = 0; j < 5; j++) stsm4(j < 4 ? fm + ((fx ^ (2 * j)) << 4) : ft, qf + 4 * j);
      fence_async_smem();
      __syncwarp();
      if (lane == 0) {
        const int row = 64 * wg + 16 * w;
        asm volatile("cp.async.bulk.tensor.2d.global.shared::cta.bulk_group [%0, {%2, %3}], [%1];"
                     ::"l"(&m.om), "r"(sb + OFF_QS + row * 128), "r"(80 * hg), "r"(128 * r + row) : "memory");
        asm volatile("cp.async.bulk.tensor.2d.global.shared::cta.bulk_group [%0, {%2, %3}], [%1];"
                     ::"l"(&m.ot), "r"(sb + OFF_QT + row * 32), "r"(80 * hg + 64), "r"(128 * r + row) : "memory");
        asm volatile("cp.async.bulk.commit_group;\ncp.async.bulk.wait_group.read 0;" ::: "memory");
      }
      TSM(true, 40 + 4 * wg + w);
      if (ENDBAR) asm volatile("bar.sync 15, 256;" ::: "memory");
    }
  }
}

typedef CUresult (*EncodeFn)(CUtensorMap*, CUtensorMapDataType, cuuint32_t, void*, const cuuint64_t*, const cuuint64_t*,
                             const cuuint32_t*, const cuuint32_t*, CUtensorMapInterleave, CUtensorMapSwizzle,
                             CUtensorMapL2promotion, CUtensorMapFloatOOBfill);

void encode(EncodeFn fn, CUtensorMap* tm, const void* base, int rank, const cuuint64_t* dims, const cuuint64_t* strides,
            const cuuint32_t* box, CUtensorMapSwizzle swz) {
  const cuuint32_t ones[3] = {1, 1, 1};
  fn(tm, CU_TENSOR_MAP_DATA_TYPE_BFLOAT16, rank, const_cast<void*>(base), dims, strides, box, ones,
     CU_TENSOR_MAP_INTERLEAVE_NONE, swz, CU_TENSOR_MAP_L2_PROMOTION_L2_128B, CU_TENSOR_MAP_FLOAT_OOB_FILL_NONE);
}

}

extern "C" void kernel_launch(void* const* d_in, const int* in_sizes, int n_in, void* d_out, int out_size) {
  (void)in_sizes; (void)n_in; (void)out_size;
  Params p;
  p.q = (const __nv_bfloat16*)d_in[0];
  p.k = (const __nv_bfloat16*)d_in[1];
  p.v = (const __nv_bfloat16*)d_in[2];
  p.shift_k = (const __nv_bfloat16*)d_in[3];
  p.ssm_k = (const __nv_bfloat16*)d_in[4];
  p.ssm_D = (const __nv_bfloat16*)d_in[5];
  p.wqkv = (const __nv_bfloat16*)d_in[7];
  p.wo = (const __nv_bfloat16*)d_in[8];
  p.gate_w = (const __nv_bfloat16*)d_in[9];
  p.out = (__nv_bfloat16*)d_out;
  p.zero = 0;

  static EncodeFn fn = nullptr;
  static void *yaddr = nullptr, *uaddr = nullptr;
  if (!fn) {
    cudaDriverEntryPointQueryResult qr;
    void* f = nullptr;
    cudaGetDriverEntryPoint("cuTensorMapEncodeTiled", &f, cudaEnableDefault, &qr);
    fn = (EncodeFn)f;
    cudaGetSymbolAddress(&yaddr, g_Y);
    cudaGetSymbolAddress(&uaddr, g_U);
    cudaFuncSetAttribute(fused_kernel, cudaFuncAttributeMaxDynamicSharedMemorySize, SMEM_BYTES);
  }
  Maps m;
  {
    const cuuint64_t dims[3] = {640, 1024, 2}, st[2] = {2560, 1280};
    const cuuint32_t box[3] = {64, 64, 2};
    encode(fn, &m.x, p.q, 3, dims, st, box, CU_TENSOR_MAP_SWIZZLE_128B);
  }
  {
    const cuuint64_t dims[3] = {640, 640, 3}, st[2] = {3840, 1280};
    const cuuint32_t box[3] = {64, 64, 3}, boxt[3] = {16, 64, 3};
    encode(fn, &m.wm, p.wqkv, 3, dims, st, box, CU_TENSOR_MAP_SWIZZLE_128B);
    encode(fn, &m.wt, p.wqkv, 3, dims, st, boxt, CU_TENSOR_MAP_SWIZZLE_32B);
  }
  {
    const cuuint64_t dims[3] = {64, 2048, 10}, st[2] = {1280, 128};
    const cuuint32_t boxk[3] = {64, 35, 1}, boxv[3] = {64, 32, 1};
    encode(fn, &m.k, p.k, 3, dims, st, boxk, CU_TENSOR_MAP_SWIZZLE_128B);
    encode(fn, &m.v, p.v, 3, dims, st, boxv, CU_TENSOR_MAP_SWIZZLE_128B);
  }
  {
    const cuuint64_t dims[3] = {16, 640, 40}, st[2] = {1280, 32};
    const cuuint32_t box[3] = {16, 40, 5};
    encode(fn, &m.wo, p.wo, 3, dims, st, box, CU_TENSOR_MAP_SWIZZLE_32B);
  }
  {
    const cuuint64_t dims[2] = {2048, 640}, st[1] = {Y_PITCH * 16};
    const cuuint32_t box[2] = {64, 80};
    encode(fn, &m.y, yaddr, 2, dims, st, box, CU_TENSOR_MAP_SWIZZLE_128B);
    const cuuint64_t stu[1] = {U_PITCH * 16};
    const cuuint32_t boxu[2] = {32, 64};
    encode(fn, &m.u, uaddr, 2, dims, stu, boxu, CU_TENSOR_MAP_SWIZZLE_NONE);
  }
  {
    const cuuint64_t dims[2] = {640, 2048}, st[1] = {1280};
    const cuuint32_t bqm[2] = {64, 128}, bqt[2] = {16, 128}, bom[2] = {64, 16}, bot[2] = {16, 16};
    encode(fn, &m.qm, p.q, 2, dims, st, bqm, CU_TENSOR_MAP_SWIZZLE_128B);
    encode(fn, &m.qt, p.q, 2, dims, st, bqt, CU_TENSOR_MAP_SWIZZLE_32B);
    encode(fn, &m.om, p.out, 2, dims, st, bom, CU_TENSOR_MAP_SWIZZLE_128B);
    encode(fn, &m.ot, p.out, 2, dims, st, bot, CU_TENSOR_MAP_SWIZZLE_32B);
  }
  fused_kernel<<<NCTA, NTHR, SMEM_BYTES>>>(m, p);
}
```

```cpp
#include <cuda.h>
#include <cuda_bf16.h>
#include <cuda_runtime.h>
#include <stdint.h>

namespace {

constexpr int SEQ = 2048, DIM = 640, NCTA = 128, NTHR = 512;

#define TRIG_KB 9
#define KV_KB 2
#define DEV_EXIT 0
#define ATT_GATE 1
#define G_AFTER 0
#define FENCE_LO 0
#define FENCE_HI 0
#define PW1 2
#define PW2 1
#define ENDBAR 0
#define PAD_KB 0
#define Y_ALIAS 1
#define H_EARLY 1
#define NOMB 0
#define SRC_ROT 0
#define WAIT_NS 0
#define WB_TRIG B_USIG
#define G_POS 0
#define TAILF 1
#define T_ISSUE 384
#define T_PF 416
#define T_INIT 448
#define ATT_MERGE 0
#define BMAP 1
#define PRE2 1
#define KV_MIX 0
#define O_DEFER 0
#define CH_W2 0
#define HALO_FIRST 1
#define PREV_EARLY 0
#define ACQ 0
#define U_TMA 0
#define U_GATE 0
#define RF_GATE 0
#define WO_TRIG B_WST
#define WL_TRIG B_WOP
#define WO_GATE 1

constexpr uint32_t STAGE_BYTES = 47104, ST_W = 16384, ST_WT = 40960;
constexpr uint32_t O_BYTES = 20480, WO_BYTES = 12800;
constexpr uint32_t OFF_OA = 0;
constexpr uint32_t OFF_QS = 3 * O_BYTES, OFF_QT = OFF_QS + 16384;
constexpr uint32_t OFF_WC = 81920;
constexpr uint32_t OFF_WA = 94720;
constexpr uint32_t OFF_GATE = 145920;
constexpr uint32_t OFF_KVX = 147968;
constexpr uint32_t OFF_D = OFF_GATE + 512;
constexpr uint32_t OFF_CH3 = 163840;
constexpr uint32_t CH_BYTES = 12288, U_BYTES = 4096;
constexpr uint32_t OFF_FT = 225280, OFF_GT = 229376;
constexpr uint32_t OFF_CH0 = 188416;
constexpr uint32_t OFF_KVS = OFF_CH0, KVS_V = 4480, KVS_BYTES = 8576;
constexpr uint32_t OFF_WS = OFF_WA;
__device__ __forceinline__ uint32_t off_us(int s) { return OFF_CH0 + 4096 * ((0x65320 >> (4 * s)) & 7); }
constexpr uint32_t OFF_YT = 163840;
constexpr uint32_t OFF_BAR = 231936;
constexpr uint32_t SMEM_BYTES = OFF_BAR + 512;

enum : uint32_t {
  B_FULL1 = 0, B_EMPTY1 = 4, B_S3 = 7, B_FULL2 = 52, B_EMPTY2 = 13, B_U = 8, B_GATE = 12, B_HA = 19, B_HB = 20,
  B_ATTN = 21, B_C34 = 22, B_CONV = 23, B_YFULL = 24, B_EPOCH = 25, B_PREP = 26, B_P1 = 27, B_LAST = 28,
  B_E3 = 29, B_OSIG = 30, B_WOP = 31, B_USIG = 32, B_WST = 33, B_KV = 34, B_KVD = 39, B_HC = 61, B_QF = 62, B_YST = 40,
  B_US = 45, B_YSIG = 50
};
constexpr uint32_t OFF_EPOCH = OFF_BAR + 8 * 51;
__device__ __forceinline__ uint32_t off_o(int j) { return j < 4 ? OFF_OA + j * O_BYTES : j < 6 ? OFF_CH0 + (j - 4) * O_BYTES : OFF_OA + (j - 6) * O_BYTES; }
__device__ __forceinline__ uint32_t off_w(int j) { return j < 4 ? OFF_WA + j * WO_BYTES : j == 4 ? OFF_KVX : j == 5 ? OFF_WC : OFF_WA + (j - 6) * WO_BYTES; }
__device__ __forceinline__ int step_src(int hg, int j) { return SRC_ROT ? (hg + j) & 7 : j == 0 ? hg : j <= hg ? j - 1 : j; }
__device__ __forceinline__ bool tail_first(int hg) { return TAILF && (hg & 3) == 3; }
__device__ __forceinline__ uint32_t off_ch(int c) { return (c < 3 ? OFF_CH0 : OFF_CH3 - 3 * CH_BYTES) + c * CH_BYTES; }

#define U_PITCH 264
__device__ __align__(1024) uint4 g_U[DIM * U_PITCH];
__device__ uint4 g_O[NCTA * 1280];
#define g_Y g_U
constexpr int Y_PITCH = U_PITCH;
__device__ uint4 g_WO[64 * 800];
__device__ uint4 g_halo[NCTA * 2 * 7 * 32];
__device__ float g_gate[SEQ + PAD_KB * 256];
__device__ unsigned g_cnt[32 * (1 + 2 * 16 + 8 + NCTA)];
constexpr int C_LAUNCH = 0, C_PREP = 32, C_Y = 32 * 17, C_W = 32 * 33, C_O = 32 * 41;

#define TSM(cond, slot) do { } while (0)
#define TSIF(cond, slot) do { if (__LINE__ >= FENCE_LO && __LINE__ < FENCE_HI) sched_fence(); } while (0)
__device__ __forceinline__ void sched_fence() {
  asm volatile("{\n.reg .pred p;\n.reg .u32 c;\nmov.u32 c, %%clock;\nsetp.eq.u32 p, c, 0;\n@p st.shared.u32 [%0], c;\n}"
               ::"r"(1024 + OFF_EPOCH + 4) : "memory");
}
#define TS(slot) TSIF(true, slot)

struct Params {
  const __nv_bfloat16 *q, *k, *v, *shift_k, *ssm_k, *ssm_D, *wqkv, *wo, *gate_w;
  __nv_bfloat16* out;
  uint32_t zero;
};

#define POLL_NS 0
constexpr int SPIN_LIMIT = 1 << 17;

__device__ __forceinline__ void mbar_init(uint32_t bar, uint32_t count) {
  asm volatile("mbarrier.init.shared::cta.b64 [%0], %1;" ::"r"(bar), "r"(count) : "memory");
}
__device__ __forceinline__ void mbar_expect_tx(uint32_t bar, uint32_t bytes) {
  asm volatile("mbarrier.arrive.expect_tx.shared::cta.b64 _, [%0], %1;" ::"r"(bar), "r"(bytes) : "memory");
}
__device__ __forceinline__ void mbar_arrive(uint32_t bar) {
  asm volatile("mbarrier.arrive.shared::cta.b64 _, [%0];" ::"r"(bar) : "memory");
}
__device__ __forceinline__ void mbar_wait(uint32_t bar, uint32_t parity) {
  uint32_t ok;
  int spins = 0;
  do {
    if (WAIT_NS)
      asm volatile("{\n.reg .pred p;\nmbarrier.try_wait.parity.shared::cta.b64 p, [%1], %2, %3;\nselp.b32 %0, 1, 0, p;\n}"
                   : "=r"(ok) : "r"(bar), "r"(parity), "r"(WAIT_NS) : "memory");
    else
      asm volatile("{\n.reg .pred p;\nmbarrier.try_wait.parity.shared::cta.b64 p, [%1], %2;\nselp.b32 %0, 1, 0, p;\n}"
                   : "=r"(ok) : "r"(bar), "r"(parity) : "memory");
    if (++spins > SPIN_LIMIT) break;
  } while (!ok);
}
__device__ __forceinline__ void flag_poll(const unsigned* p, unsigned target) {
  unsigned v;
  int spins = 0;
  do {
    if (POLL_NS && spins) __nanosleep(POLL_NS);
    asm volatile("ld.relaxed.gpu.global.u32 %0, [%1];" : "=r"(v) : "l"(p) : "memory");
    if (++spins > SPIN_LIMIT) break;
  } while ((int)(v - target) < 0);
}
__device__ __forceinline__ void flag_wait(const unsigned* p, unsigned target) {
  flag_poll(p, target);
  if (ACQ) asm volatile("fence.acquire.gpu;\nfence.proxy.async.global;" ::: "memory");
}
__device__ __forceinline__ void flag_signal(unsigned* p, int n, int lane) {
  if (lane == 0) asm volatile("fence.release.gpu;" ::: "memory");
  __syncwarp();
  if (lane < n) asm volatile("red.relaxed.gpu.global.add.u32 [%0], 1;" ::"l"(p + 32 * lane) : "memory");
}
__device__ __forceinline__ void flag_bump(unsigned* p) {
  asm volatile("red.relaxed.gpu.global.add.u32 [%0], 1;" ::"l"(p) : "memory");
}
__device__ __forceinline__ void fence_async_smem() { asm volatile("fence.proxy.async.shared::cta;" ::: "memory"); }
__device__ __forceinline__ void wg_sync(int id) { asm volatile("bar.sync %0, 128;" ::"r"(id) : "memory"); }

__device__ __forceinline__ void tma_2d(uint32_t dst, const CUtensorMap* tm, int c0, int c1, uint32_t bar) {
  asm volatile("cp.async.bulk.tensor.2d.shared::cluster.global.mbarrier::complete_tx::bytes [%0], [%1, {%3, %4}], [%2];"
               ::"r"(dst), "l"(tm), "r"(bar), "r"(c0), "r"(c1) : "memory");
}
__device__ __forceinline__ void tma_3d(uint32_t dst, const CUtensorMap* tm, int c0, int c1, int c2, uint32_t bar) {
  asm volatile("cp.async.bulk.tensor.3d.shared::cluster.global.mbarrier::complete_tx::bytes [%0], [%1, {%3, %4, %5}], [%2];"
               ::"r"(dst), "l"(tm), "r"(bar), "r"(c0), "r"(c1), "r"(c2) : "memory");
}
__device__ __forceinline__ void bulk_load(uint32_t dst, const void* src, uint32_t bytes, uint32_t bar) {
  asm volatile("cp.async.bulk.shared::cluster.global.mbarrier::complete_tx::bytes [%0], [%1], %2, [%3];"
               ::"r"(dst), "l"(src), "r"(bytes), "r"(bar) : "memory");
}
__device__ __forceinline__ void tm_prefetch(const CUtensorMap* tm) {
  asm volatile("prefetch.tensormap [%0];" ::"l"(tm) : "memory");
}

__device__ __forceinline__ void wg_fence() { asm volatile("wgmma.fence.sync.aligned;" ::: "memory"); }
__device__ __forceinline__ void wg_commit() { asm volatile("wgmma.commit_group.sync.aligned;" ::: "memory"); }
template <int N> __device__ __forceinline__ void wg_wait() { asm volatile("wgmma.wait_group.sync.aligned %0;" ::"n"(N) : "memory"); }
__device__ __forceinline__ uint32_t desc_lo(uint32_t addr, uint32_t lbo) { return ((addr & 0x3FFFF) >> 4) | ((lbo >> 4) << 16); }
constexpr uint32_t desc_hi(uint32_t sbo, uint32_t swz) { return (sbo >> 4) | (swz << 30); }
constexpr uint32_t HI_SW128 = desc_hi(1024, 1), HI_SW64 = desc_hi(512, 2), HI_SW32 = desc_hi(256, 3), HI_NONE = desc_hi(128, 0);
template <int N> __device__ __forceinline__ void pin(float* d) {
#pragma unroll
  for (int i = 0; i < N; i++) asm volatile("" : "+f"(d[i])::"memory");
}

__device__ __forceinline__ uint32_t lds32(uint32_t a) {
  uint32_t v;
  asm volatile("ld.volatile.shared.u32 %0, [%1];" : "=r"(v) : "r"(a) : "memory");
  return v;
}
__device__ __forceinline__ uint4 ldg128(const void* a) {
  uint4 v;
  asm volatile("ld.global.nc.v4.u32 {%0, %1, %2, %3}, [%4];" : "=r"(v.x), "=r"(v.y), "=r"(v.z), "=r"(v.w) : "l"(a) : "memory");
  return v;
}
__device__ __forceinline__ uint2 ldg64(const void* a) {
  uint2 v;
  asm volatile("ld.global.nc.v2.u32 {%0, %1}, [%2];" : "=r"(v.x), "=r"(v.y) : "l"(a) : "memory");
  return v;
}
__device__ __forceinline__ void ldsm4(uint32_t* r, uint32_t a) {
  asm volatile("ldmatrix.sync.aligned.m8n8.x4.shared.b16 {%0, %1, %2, %3}, [%4];"
               : "=r"(r[0]), "=r"(r[1]), "=r"(r[2]), "=r"(r[3]) : "r"(a) : "memory");
}
__device__ __forceinline__ void ldsm4t(uint32_t* r, uint32_t a) {
  asm volatile("ldmatrix.sync.aligned.m8n8.x4.trans.shared.b16 {%0, %1, %2, %3}, [%4];"
               : "=r"(r[0]), "=r"(r[1]), "=r"(r[2]), "=r"(r[3]) : "r"(a) : "memory");
}
__device__ __forceinline__ uint4 lds128(uint32_t a) {
  uint4 v;
  asm volatile("ld.shared.v4.u32 {%0, %1, %2, %3}, [%4];" : "=r"(v.x), "=r"(v.y), "=r"(v.z), "=r"(v.w) : "r"(a) : "memory");
  return v;
}
__device__ __forceinline__ void sts128(uint32_t a, uint32_t x, uint32_t y, uint32_t z, uint32_t w) {
  asm volatile("st.shared.v4.u32 [%0], {%1, %2, %3, %4};" ::"r"(a), "r"(x), "r"(y), "r"(z), "r"(w) : "memory");
}
__device__ __forceinline__ void stsm4(uint32_t a, const uint32_t* r) {
  asm volatile("stmatrix.sync.aligned.m8n8.x4.shared.b16 [%0], {%1, %2, %3, %4};" ::"r"(a), "r"(r[0]), "r"(r[1]), "r"(r[2]), "r"(r[3]) : "memory");
}
__device__ __forceinline__ void stsm4t(uint32_t a, const uint32_t* r) {
  asm volatile("stmatrix.sync.aligned.m8n8.x4.trans.shared.b16 [%0], {%1, %2, %3, %4};" ::"r"(a), "r"(r[0]), "r"(r[1]), "r"(r[2]), "r"(r[3]) : "memory");
}
__device__ __forceinline__ uint32_t pack2(float lo, float hi) {
  uint32_t r;
  asm("cvt.rn.bf16x2.f32 %0, %1, %2;" : "=r"(r) : "f"(hi), "f"(lo));
  return r;
}
__device__ __forceinline__ uint32_t movm(uint32_t a) {
  uint32_t d;
  asm volatile("movmatrix.sync.aligned.m8n8.trans.b16 %0, %1;" : "=r"(d) : "r"(a));
  return d;
}
__device__ __forceinline__ uint32_t bmul(uint32_t a, uint32_t b) {
  uint32_t d;
  asm("mul.rn.bf16x2 %0, %1, %2;" : "=r"(d) : "r"(a), "r"(b));
  return d;
}
__device__ __forceinline__ uint32_t badd(uint32_t a, uint32_t b) {
  uint32_t d;
  asm("add.rn.bf16x2 %0, %1, %2;" : "=r"(d) : "r"(a), "r"(b));
  return d;
}
__device__ __forceinline__ float bf_lo(uint32_t x) { return __uint_as_float(x << 16); }
__device__ __forceinline__ float bf_hi(uint32_t x) { return __uint_as_float(x & 0xFFFF0000u); }
__device__ __forceinline__ float ex2(float x) {
  float y;
  asm("ex2.approx.ftz.f32 %0, %1;" : "=f"(y) : "f"(x));
  return y;
}
__device__ __forceinline__ float rcp(float x) {
  float y;
  asm("rcp.approx.ftz.f32 %0, %1;" : "=f"(y) : "f"(x));
  return y;
}
__device__ __forceinline__ void mma16816(float* d, uint32_t a0, uint32_t a1, uint32_t a2, uint32_t a3, uint32_t b0, uint32_t b1) {
  asm volatile("mma.sync.aligned.m16n8k16.row.col.f32.bf16.bf16.f32 {%0, %1, %2, %3}, {%4, %5, %6, %7}, {%8, %9}, {%0, %1, %2, %3};"
               : "+f"(d[0]), "+f"(d[1]), "+f"(d[2]), "+f"(d[3])
               : "r"(a0), "r"(a1), "r"(a2), "r"(a3), "r"(b0), "r"(b1));
}
__device__ __forceinline__ void mma1688(float* d, uint32_t a0, uint32_t a1, uint32_t b0) {
  asm volatile("mma.sync.aligned.m16n8k8.row.col.f32.bf16.bf16.f32 {%0, %1, %2, %3}, {%4, %5}, {%6}, {%0, %1, %2, %3};"
               : "+f"(d[0]), "+f"(d[1]), "+f"(d[2]), "+f"(d[3])
               : "r"(a0), "r"(a1), "r"(b0));
}

template <int N> struct WgRS;
template <int N> struct WgSST;
template <> struct WgRS<32> {
  template <uint32_t HB>
  static __device__ __forceinline__ void mma(float* d, const uint32_t* a, uint32_t db) {
    asm volatile("{\n.reg .pred p;\n.reg .b64 db;\nsetp.ne.b32 p, %22, 0;\n"
      "mov.b64 db, {%20, %21};\n"
      "wgmma.mma_async.sync.aligned.m64n32k16.f32.bf16.bf16 {"
      "%0, %1, %2, %3, %4, %5, %6, %7, %8, %9, %10, %11, %12, %13, %14, %15"
      "}, {%16, %17, %18, %19}, db, p, 1, 1, 1;\n}\n"
      : "+f"(d[0]), "+f"(d[1]), "+f"(d[2]), "+f"(d[3]), "+f"(d[4]), "+f"(d[5]), "+f"(d[6]), "+f"(d[7]),
        "+f"(d[8]), "+f"(d[9]), "+f"(d[10]), "+f"(d[11]), "+f"(d[12]), "+f"(d[13]), "+f"(d[14]), "+f"(d[15])
      : "r"(a[0]), "r"(a[1]), "r"(a[2]), "r"(a[3]), "r"(db), "n"(HB), "n"(1));
  }
  template <uint32_t HB>
  static __device__ __forceinline__ void set(float* d, const uint32_t* a, uint32_t db) {
    asm volatile("{\n.reg .pred p;\n.reg .b64 db;\nsetp.ne.b32 p, %22, 0;\n"
      "mov.b64 db, {%20, %21};\n"
      "wgmma.mma_async.sync.aligned.m64n32k16.f32.bf16.bf16 {"
      "%0, %1, %2, %3, %4, %5, %6, %7, %8, %9, %10, %11, %12, %13, %14, %15"
      "}, {%16, %17, %18, %19}, db, p, 1, 1, 1;\n}\n"
      : "=f"(d[0]), "=f"(d[1]), "=f"(d[2]), "=f"(d[3]), "=f"(d[4]), "=f"(d[5]), "=f"(d[6]), "=f"(d[7]),
        "=f"(d[8]), "=f"(d[9]), "=f"(d[10]), "=f"(d[11]), "=f"(d[12]), "=f"(d[13]), "=f"(d[14]), "=f"(d[15])
      : "r"(a[0]), "r"(a[1]), "r"(a[2]), "r"(a[3]), "r"(db), "n"(HB), "n"(0));
  }
};
template <> struct WgRS<64> {
  template <uint32_t HB>
  static __device__ __forceinline__ void mma(float* d, const uint32_t* a, uint32_t db) {
    asm volatile("{\n.reg .pred p;\n.reg .b64 db;\nsetp.ne.b32 p, %38, 0;\n"
      "mov.b64 db, {%36, %37};\n"
      "wgmma.mma_async.sync.aligned.m64n64k16.f32.bf16.bf16 {"
      "%0, %1, %2, %3, %4, %5, %6, %7, %8, %9, %10, %11, %12, %13, %14, %15, "
      "%16, %17, %18, %19, %20, %21, %22, %23, %24, %25, %26, %27, %28, %29, %30, %31"
      "}, {%32, %33, %34, %35}, db, p, 1, 1, 1;\n}\n"
      : "+f"(d[0]), "+f"(d[1]), "+f"(d[2]), "+f"(d[3]), "+f"(d[4]), "+f"(d[5]), "+f"(d[6]), "+f"(d[7]),
        "+f"(d[8]), "+f"(d[9]), "+f"(d[10]), "+f"(d[11]), "+f"(d[12]), "+f"(d[13]), "+f"(d[14]), "+f"(d[15]),
        "+f"(d[16]), "+f"(d[17]), "+f"(d[18]), "+f"(d[19]), "+f"(d[20]), "+f"(d[21]), "+f"(d[22]), "+f"(d[23]),
        "+f"(d[24]), "+f"(d[25]), "+f"(d[26]), "+f"(d[27]), "+f"(d[28]), "+f"(d[29]), "+f"(d[30]), "+f"(d[31])
      : "r"(a[0]), "r"(a[1]), "r"(a[2]), "r"(a[3]), "r"(db), "n"(HB), "n"(1));
  }
  template <uint32_t HB>
  static __device__ __forceinline__ void set(float* d, const uint32_t* a, uint32_t db) {
    asm volatile("{\n.reg .pred p;\n.reg .b64 db;\nsetp.ne.b32 p, %38, 0;\n"
      "mov.b64 db, {%36, %37};\n"
      "wgmma.mma_async.sync.aligned.m64n64k16.f32.bf16.bf16 {"
      "%0, %1, %2, %3, %4, %5, %6, %7, %8, %9, %10, %11, %12, %13, %14, %15, "
      "%16, %17, %18, %19, %20, %21, %22, %23, %24, %25, %26, %27, %28, %29, %30, %31"
      "}, {%32, %33, %34, %35}, db, p, 1, 1, 1;\n}\n"
      : "=f"(d[0]), "=f"(d[1]), "=f"(d[2]), "=f"(d[3]), "=f"(d[4]), "=f"(d[5]), "=f"(d[6]), "=f"(d[7]),
        "=f"(d[8]), "=f"(d[9]), "=f"(d[10]), "=f"(d[11]), "=f"(d[12]), "=f"(d[13]), "=f"(d[14]), "=f"(d[15]),
        "=f"(d[16]), "=f"(d[17]), "=f"(d[18]), "=f"(d[19]), "=f"(d[20]), "=f"(d[21]), "=f"(d[22]), "=f"(d[23]),
        "=f"(d[24]), "=f"(d[25]), "=f"(d[26]), "=f"(d[27]), "=f"(d[28]), "=f"(d[29]), "=f"(d[30]), "=f"(d[31])
      : "r"(a[0]), "r"(a[1]), "r"(a[2]), "r"(a[3]), "r"(db), "n"(HB), "n"(0));
  }
};
template <> struct WgSST<48> {
  template <uint32_t HA, uint32_t HB>
  static __device__ __forceinline__ void mma(float* d, uint32_t da, uint32_t db, int sc) {
    asm volatile("{\n.reg .pred p;\n.reg .b64 da, db;\nsetp.ne.b32 p, %28, 0;\n"
      "mov.b64 da, {%24, %25};\nmov.b64 db, {%26, %27};\n"
      "wgmma.mma_async.sync.aligned.m64n48k16.f32.bf16.bf16 {"
      "%0, %1, %2, %3, %4, %5, %6, %7, %8, %9, %10, %11, %12, %13, %14, %15, "
      "%16, %17, %18, %19, %20, %21, %22, %23"
      "}, da, db, p, 1, 1, 0, 1;\n}\n"
      : "+f"(d[0]), "+f"(d[1]), "+f"(d[2]), "+f"(d[3]), "+f"(d[4]), "+f"(d[5]), "+f"(d[6]), "+f"(d[7]),
        "+f"(d[8]), "+f"(d[9]), "+f"(d[10]), "+f"(d[11]), "+f"(d[12]), "+f"(d[13]), "+f"(d[14]), "+f"(d[15]),
        "+f"(d[16]), "+f"(d[17]), "+f"(d[18]), "+f"(d[19]), "+f"(d[20]), "+f"(d[21]), "+f"(d[22]), "+f"(d[23])
      : "r"(da), "n"(HA), "r"(db), "n"(HB), "r"(sc));
  }
};
template <> struct WgSST<80> {
  template <uint32_t HA, uint32_t HB>
  static __device__ __forceinline__ void mma(float* d, uint32_t da, uint32_t db, int sc) {
    asm volatile("{\n.reg .pred p;\n.reg .b64 da, db;\nsetp.ne.b32 p, %44, 0;\n"
      "mov.b64 da, {%40, %41};\nmov.b64 db, {%42, %43};\n"
      "wgmma.mma_async.sync.aligned.m64n80k16.f32.bf16.bf16 {"
      "%0, %1, %2, %3, %4, %5, %6, %7, %8, %9, %10, %11, %12, %13, %14, %15, "
      "%16, %17, %18, %19, %20, %21, %22, %23, %24, %25, %26, %27, %28, %29, %30, %31, "
      "%32, %33, %34, %35, %36, %37, %38, %39"
      "}, da, db, p, 1, 1, 0, 1;\n}\n"
      : "+f"(d[0]), "+f"(d[1]), "+f"(d[2]), "+f"(d[3]), "+f"(d[4]), "+f"(d[5]), "+f"(d[6]), "+f"(d[7]),
        "+f"(d[8]), "+f"(d[9]), "+f"(d[10]), "+f"(d[11]), "+f"(d[12]), "+f"(d[13]), "+f"(d[14]), "+f"(d[15]),
        "+f"(d[16]), "+f"(d[17]), "+f"(d[18]), "+f"(d[19]), "+f"(d[20]), "+f"(d[21]), "+f"(d[22]), "+f"(d[23]),
        "+f"(d[24]), "+f"(d[25]), "+f"(d[26]), "+f"(d[27]), "+f"(d[28]), "+f"(d[29]), "+f"(d[30]), "+f"(d[31]),
        "+f"(d[32]), "+f"(d[33]), "+f"(d[34]), "+f"(d[35]), "+f"(d[36]), "+f"(d[37]), "+f"(d[38]), "+f"(d[39])
      : "r"(da), "n"(HA), "r"(db), "n"(HB), "r"(sc));
  }
};
template <> struct WgSST<192> {
  template <uint32_t HA, uint32_t HB>
  static __device__ __forceinline__ void mma(float* d, uint32_t da, uint32_t db, int sc) {
    asm volatile("{\n.reg .pred p;\n.reg .b64 da, db;\nsetp.ne.b32 p, %100, 0;\n"
      "mov.b64 da, {%96, %97};\nmov.b64 db, {%98, %99};\n"
      "wgmma.mma_async.sync.aligned.m64n192k16.f32.bf16.bf16 {"
      "%0, %1, %2, %3, %4, %5, %6, %7, %8, %9, %10, %11, %12, %13, %14, %15, "
      "%16, %17, %18, %19, %20, %21, %22, %23, %24, %25, %26, %27, %28, %29, %30, %31, "
      "%32, %33, %34, %35, %36, %37, %38, %39, %40, %41, %42, %43, %44, %45, %46, %47, "
      "%48, %49, %50, %51, %52, %53, %54, %55, %56, %57, %58, %59, %60, %61, %62, %63, "
      "%64, %65, %66, %67, %68, %69, %70, %71, %72, %73, %74, %75, %76, %77, %78, %79, "
      "%80, %81, %82, %83, %84, %85, %86, %87, %88, %89, %90, %91, %92, %93, %94, %95"
      "}, da, db, p, 1, 1, 0, 1;\n}\n"
      : "+f"(d[0]), "+f"(d[1]), "+f"(d[2]), "+f"(d[3]), "+f"(d[4]), "+f"(d[5]), "+f"(d[6]), "+f"(d[7]),
        "+f"(d[8]), "+f"(d[9]), "+f"(d[10]), "+f"(d[11]), "+f"(d[12]), "+f"(d[13]), "+f"(d[14]), "+f"(d[15]),
        "+f"(d[16]), "+f"(d[17]), "+f"(d[18]), "+f"(d[19]), "+f"(d[20]), "+f"(d[21]), "+f"(d[22]), "+f"(d[23]),
        "+f"(d[24]), "+f"(d[25]), "+f"(d[26]), "+f"(d[27]), "+f"(d[28]), "+f"(d[29]), "+f"(d[30]), "+f"(d[31]),
        "+f"(d[32]), "+f"(d[33]), "+f"(d[34]), "+f"(d[35]), "+f"(d[36]), "+f"(d[37]), "+f"(d[38]), "+f"(d[39]),
        "+f"(d[40]), "+f"(d[41]), "+f"(d[42]), "+f"(d[43]), "+f"(d[44]), "+f"(d[45]), "+f"(d[46]), "+f"(d[47]),
        "+f"(d[48]), "+f"(d[49]), "+f"(d[50]), "+f"(d[51]), "+f"(d[52]), "+f"(d[53]), "+f"(d[54]), "+f"(d[55]),
        "+f"(d[56]), "+f"(d[57]), "+f"(d[58]), "+f"(d[59]), "+f"(d[60]), "+f"(d[61]), "+f"(d[62]), "+f"(d[63]),
        "+f"(d[64]), "+f"(d[65]), "+f"(d[66]), "+f"(d[67]), "+f"(d[68]), "+f"(d[69]), "+f"(d[70]), "+f"(d[71]),
        "+f"(d[72]), "+f"(d[73]), "+f"(d[74]), "+f"(d[75]), "+f"(d[76]), "+f"(d[77]), "+f"(d[78]), "+f"(d[79]),
        "+f"(d[80]), "+f"(d[81]), "+f"(d[82]), "+f"(d[83]), "+f"(d[84]), "+f"(d[85]), "+f"(d[86]), "+f"(d[87]),
        "+f"(d[88]), "+f"(d[89]), "+f"(d[90]), "+f"(d[91]), "+f"(d[92]), "+f"(d[93]), "+f"(d[94]), "+f"(d[95])
      : "r"(da), "n"(HA), "r"(db), "n"(HB), "r"(sc));
  }
};

struct FftConst {
  uint32_t f[2][4], fi[4][4];
  float ta[4], tb[4];
};
__device__ __forceinline__ void cis(int m, float scale, float& c, float& s) {
  const float a = (float)m * (-6.283185307179586f * scale);
  c = __cosf(a);
  s = __sinf(a);
}
__device__ __forceinline__ void fft_tables(uint32_t (&v)[12], int tw) {
  const int row = tw >> 2, ch = tw & 3;
#pragma unroll
  for (int i = 0; i < 4; i++) {
    float c[2], s[2], x[2];
#pragma unroll
    for (int e = 0; e < 2; e++) {
      cis((((32 * (8 * ch + 2 * i + e) + 15) * (4 * row - 63) + 2048) & 4095) - 2048, 1.f / 4096, c[e], s[e]);
      float gc, gs;
      cis((((row & 15) * (8 * (ch & 1) + 2 * i + e) + 8) & 15) - 8, 1.f / 16, gc, gs);
      x[e] = (row >> 4) == (ch >> 1) ? gc : (ch >> 1) ? gs : -gs;
    }
    v[i] = pack2(c[0] * 0.125f, c[1] * 0.125f);
    v[4 + i] = pack2(s[0] * 0.125f, s[1] * 0.125f);
    v[8 + i] = pack2(x[0], x[1]);
  }
#pragma unroll
  for (int i = 0; i < 12; i++) asm volatile("" : "+r"(v[i]));
}
__device__ __forceinline__ void fft_tables_store(const uint32_t (&v)[12], uint32_t sb, int tw) {
  const int row = tw >> 2;
  const uint32_t x = ((tw ^ (row >> 1)) & 3) << 4, a = sb + OFF_FT + (16 * (row >> 3) + (row & 7)) * 64 + x;
  sts128(a, v[0], v[1], v[2], v[3]);
  sts128(a + 512, v[4], v[5], v[6], v[7]);
  sts128(sb + OFF_GT + row * 64 + x, v[8], v[9], v[10], v[11]);
}
__device__ __forceinline__ void fft_twiddles(FftConst& k, int w, int lane) {
#pragma unroll
  for (int i = 0; i < 4; i++) {
    float c, s;
    cis((2 * (8 * (i >> 1) + 2 * (lane & 3) + (i & 1)) - 15) * (4 * (8 * w + (lane >> 2)) - 63), 1.f / 4096, c, s);
    k.ta[i] = __fdividef(-s, 1.f + c);
    k.tb[i] = s;
  }
  pin<4>(k.ta);
  pin<4>(k.tb);
}
__device__ __forceinline__ void fft_matrices(FftConst& k, uint32_t sb, int w, int lane) {
  const uint32_t x = (lane >> 1) & 3;
#pragma unroll
  for (int i = 0; i < 2; i++) {
    ldsm4(k.f[i], sb + OFF_FT + (16 * w + (lane & 15)) * 64 + (((2 * i + (lane >> 4)) ^ x) << 4));
    ldsm4t(k.fi[i], sb + OFF_FT + (32 * i + lane) * 64 + ((w ^ x) << 4));
#pragma unroll
    for (int j = 0; j < 4; j++) {
      k.fi[2 + i][j] = (j & 1) ? k.fi[i][j - 1] ^ 0x80008000u : k.fi[i][j + 1];
      asm volatile("" : "+r"(k.fi[2 + i][j]));
    }
  }
}
template <bool INV> __device__ __forceinline__ void rot(float& x, float& y, float a, float b) {
  x = fmaf(INV ? -a : a, y, x);
  y = fmaf(INV ? -b : b, x, y);
  x = fmaf(INV ? -a : a, y, x);
}
__device__ __forceinline__ void twiddle_fwd(uint32_t (&a)[4][4], float* d, const FftConst& k) {
#pragma unroll
  for (int q = 0; q < 4; q++)
#pragma unroll
    for (int j = 0; j < 2; j++) {
      float* x = d + 8 * q + 4 * j;
      rot<false>(x[0], x[2], k.ta[2 * j], k.tb[2 * j]);
      rot<false>(x[1], x[3], k.ta[2 * j + 1], k.tb[2 * j + 1]);
      a[q & 2][2 * j + (q & 1)] = pack2(x[0], x[1]);
      a[(q & 2) + 1][2 * j + (q & 1)] = pack2(x[2], x[3]);
    }
}
__device__ __forceinline__ void g_step(float* d, const uint32_t (&a)[4][4], uint32_t dre, uint32_t dim) {
  WgRS<32>::set<HI_SW64>(d, a[0], dre);
  WgRS<32>::set<HI_SW64>(d + 16, a[2], dre);
  WgRS<32>::mma<HI_SW64>(d, a[1], dim);
  WgRS<32>::mma<HI_SW64>(d + 16, a[3], dim);
  wg_commit();
}

__device__ __forceinline__ void conv_channel(const FftConst& k, uint32_t sb, int c, int wg, int w, int lane) {
  const uint32_t cb = sb + off_ch(c), bars = sb + OFF_BAR;
  const uint32_t du = desc_lo(cb, 1024), dg = desc_lo(sb + OFF_GT, 16), dz = desc_lo(cb + U_BYTES, 16);
  float U[32], H[32];
  uint32_t a[4][4], e[4][4];
  const float dv = __uint_as_float(lds32(sb + OFF_D + 4 * c));
  wg_fence();
  WgRS<64>::set<HI_SW32>(H, k.f[0], du + 256);
  WgRS<64>::mma<HI_SW32>(H, k.f[1], du + 256 + 32);
  wg_commit();
  wg_wait<0>();
  pin<32>(H);
  TSM(w == 0 && c == 1, 114);
  twiddle_fwd(a, H, k);
  asm volatile("" : "+r"(a[0][0]), "+r"(a[1][1]), "+r"(a[2][2]), "+r"(a[3][3]));
  TSM(w == 0 && c == 1, 127);
  if (ATT_GATE && H_EARLY) mbar_wait(bars + 8 * B_ATTN, 0);
  mbar_wait(bars + 8 * (B_U + (c < 3 ? c : 3)), 0);
  TSM(w == 0 && c < 3, 7 + wg);
  wg_fence();
  WgRS<64>::set<HI_SW32>(U, k.f[0], du);
  WgRS<64>::mma<HI_SW32>(U, k.f[1], du + 32);
  wg_commit();
  g_step(H, a, dg, dg + 64);
  wg_wait<1>();
  pin<32>(U);
  twiddle_fwd(e, U, k);
  wg_fence();
  g_step(U, e, dg, dg + 64);
  wg_wait<0>();
  pin<32>(U);
  pin<32>(H);
#pragma unroll
  for (int j = 0; j < 2; j++) {
    float pr[4][2], pi[4][2];
#pragma unroll
    for (int x = 0; x < 2; x++) {
      H[4 * j + x] += dv;
#pragma unroll
      for (int m = 0; m < 4; m++) {
#pragma unroll
        for (int q = 0; q <= m; q++) {
          const int ih = 16 * (q >> 1) + 2 * (q & 1) + 4 * j + x, iu = 16 * ((m - q) >> 1) + 2 * ((m - q) & 1) + 4 * j + x;
          pr[m][x] = q ? fmaf(H[ih], U[iu], pr[m][x]) : H[ih] * U[iu];
          pi[m][x] = q ? fmaf(H[ih], U[iu + 8], pi[m][x]) : H[ih] * U[iu + 8];
          pr[m][x] = fmaf(-H[ih + 8], U[iu + 8], pr[m][x]);
          pi[m][x] = fmaf(H[ih + 8], U[iu], pi[m][x]);
        }
      }
    }
#pragma unroll
    for (int m = 0; m < 4; m++) {
      a[m & 2][2 * j + (m & 1)] = pack2(pr[m][0], pr[m][1]);
      a[(m & 2) + 1][2 * j + (m & 1)] = pack2(pi[m][0], pi[m][1]);
    }
  }
  wg_fence();
  g_step(U, a, dg + 64, dg);
  const uint32_t za = cb + U_BYTES + (8 * w + (lane & 7)) * 128 + (((lane >> 3) ^ (lane & 7)) << 4);
  const uint32_t ya = cb + (lane >> 4) * 1024 + (8 * w + (lane & 7)) * 32 + ((((lane >> 3) ^ (lane >> 2)) & 1) << 4);
  wg_sync(1 + wg);
  wg_wait<0>();
  pin<32>(U);
  TSIF(w == 0, 80 + c);
#pragma unroll
  for (int p = 0; p < 2; p++) {
#pragma unroll
    for (int i = 0; i < 4; i++) {
      const int j = i & 1;
      float* x = U + 16 * p + 4 * j + (i & 2);
      rot<true>(x[8], x[0], k.ta[2 * j], k.tb[2 * j]);
      rot<true>(x[9], x[1], k.ta[2 * j + 1], k.tb[2 * j + 1]);
      e[p][i] = pack2(x[8], x[9]);
      e[2 + p][i] = pack2(x[0], x[1]);
    }
    stsm4(za ^ (64 * p), e[p]);
    stsm4((za ^ (64 * p)) + 4096, e[2 + p]);
  }
  fence_async_smem();
  wg_sync(1 + wg);
  wg_fence();
  WgRS<64>::set<HI_SW128>(H, k.fi[0], dz);
#pragma unroll
  for (int ks = 1; ks < 4; ks++) WgRS<64>::mma<HI_SW128>(H, k.fi[ks], dz + 128 * ks);
  wg_commit();
  wg_wait<0>();
  pin<32>(H);
  TSIF(w == 0, 88 + c);
#pragma unroll
  for (int j = 0; j < 8; j++)
    a[j >> 2][j & 3] = j < 2 ? pack2(H[4 * j], H[4 * j + 1]) : pack2(H[4 * j] + H[4 * j - 6], H[4 * j + 1] + H[4 * j - 5]);
  stsm4(ya, a[0]);
  stsm4(ya + 2048, a[1]);
  fence_async_smem();
  __syncwarp();
}

__device__ __forceinline__ void prep_slab(uint4* res, const uint2* sw, uint32_t sb, int slab, int w, int lane) {
  const int t = lane & 3, tp = (lane & 7) >> 1, pos = 8 * tp + 2 * (((lane >> 3) + tp) & 3) + (lane & 1);
  const uint32_t base = sb + OFF_KVS + slab * KVS_BYTES + pos * 128;
  uint32_t kk[2][4][4], vv[2][4];
  mbar_wait(sb + OFF_BAR + 8 * (B_KV + slab), 0);
#pragma unroll
  for (int h = 0; h < 2; h++) {
#pragma unroll
    for (int j = 0; j < 4; j++) {
      const uint32_t a = base + 128 * j;
      ldsm4t(kk[h][j], a + (((w + 4 * h) ^ ((a >> 7) & 7)) << 4));
    }
    const uint32_t a = base + KVS_V;
    ldsm4t(vv[h], a + (((w + 4 * h) ^ ((a >> 7) & 7)) << 4));
  }
#pragma unroll
  for (int h = 0; h < 2; h++) {
    uint32_t (&k)[4][4] = kk[h];
    uint32_t (&v)[4] = vv[h];
    const uint32_t w0 = __byte_perm(sw[h].x, 0, 0x1010), w1 = __byte_perm(sw[h].x, 0, 0x3232);
    const uint32_t w2 = __byte_perm(sw[h].y, 0, 0x1010), w3 = __byte_perm(sw[h].y, 0, 0x3232);
#pragma unroll
    for (int m = 0; m < 4; m++)
      v[m] = bmul(badd(badd(badd(bmul(k[0][m], w3), bmul(k[1][m], w2)), bmul(k[2][m], w1)), bmul(k[3][m], w0)), v[m]);
    uint32_t a[4];
#pragma unroll
    for (int m = 0; m < 4; m++) a[m] = (t & 1) ? v[(m + 3) & 3] : v[m];
    res[h] = (t & 2) ? make_uint4(a[2], a[3], a[0], a[1]) : make_uint4(a[0], a[1], a[2], a[3]);
  }
}

__device__ __forceinline__ void prep_gate(const Params& p, int b, int w, int lane) {
  uint2 gw[5], x[4][5];
#pragma unroll
  for (int j = 0; j < 5; j++) gw[j] = ldg64(reinterpret_cast<const uint2*>(p.gate_w) + lane + 32 * j);
#pragma unroll
  for (int i = 0; i < 4; i++)
#pragma unroll
    for (int j = 0; j < 5; j++)
      x[i][j] = ldg64(reinterpret_cast<const uint2*>(p.q) + (16 * b + 4 * w + i) * (DIM / 4) + lane + 32 * j);
  float s[4];
#pragma unroll
  for (int i = 0; i < 4; i++) {
    s[i] = 0.f;
#pragma unroll
    for (int j = 0; j < 5; j++) {
      const uint32_t m0 = bmul(x[i][j].x, gw[j].x), m1 = bmul(x[i][j].y, gw[j].y);
      s[i] += (bf_lo(m0) + bf_hi(m0)) + (bf_lo(m1) + bf_hi(m1));
    }
  }
  const bool h = lane & 16, q = lane & 8;
  const float a = (h ? s[2] : s[0]) + __shfl_xor_sync(0xffffffffu, h ? s[0] : s[2], 16);
  const float c = (h ? s[3] : s[1]) + __shfl_xor_sync(0xffffffffu, h ? s[1] : s[3], 16);
  float z = (q ? c : a) + __shfl_xor_sync(0xffffffffu, q ? a : c, 8);
#pragma unroll
  for (int o = 4; o > 0; o >>= 1) z += __shfl_xor_sync(0xffffffffu, z, o);
  z = bf_lo(pack2(z, 0.f));
  if ((lane & 7) == 0) g_gate[16 * b + 4 * w + (lane >> 3)] = bf_lo(pack2(__fdividef(1.f, 1.f + __expf(-z)), 0.f));
}

__device__ __forceinline__ uint32_t bmax(uint32_t a, uint32_t b) {
  uint32_t d;
  asm("max.bf16x2 %0, %1, %2;" : "=r"(d) : "r"(a), "r"(b));
  return d;
}
__device__ __forceinline__ void softmax_two(const float (&l)[2][2], uint32_t& p0, uint32_t& p1) {
  constexpr float kScale = 0.22360679774997896f, kLog2e = 1.4426950408889634f;
  const uint32_t r0 = pack2(l[0][0], l[1][0]), r1 = pack2(l[0][1], l[1][1]);
  const uint32_t x0 = pack2(bf_lo(r0) * kScale, bf_hi(r0) * kScale), x1 = pack2(bf_lo(r1) * kScale, bf_hi(r1) * kScale);
  uint32_t m = bmax(x0, x1);
  m = bmax(m, __shfl_xor_sync(0xffffffffu, m, 1));
  m = bmax(m, __shfl_xor_sync(0xffffffffu, m, 2));
  const float m0 = bf_lo(m) * kLog2e, m1 = bf_hi(m) * kLog2e;
  p0 = pack2(ex2(bf_lo(x0) * kLog2e - m0), ex2(bf_lo(x1) * kLog2e - m0));
  p1 = pack2(ex2(bf_hi(x0) * kLog2e - m1), ex2(bf_hi(x1) * kLog2e - m1));
}

__device__ __forceinline__ void halo_read(uint32_t (&kpv)[10], uint32_t (&vpv)[10], uint32_t (&tg)[7], const uint4* hp) {
#pragma unroll
  for (int j = 0; j < 7; j++) {
    uint32_t x0, x1, x2;
    asm volatile("ld.relaxed.gpu.global.v4.u32 {%0, %1, %2, %3}, [%4];"
                 : "=r"(x0), "=r"(x1), "=r"(x2), "=r"(tg[j]) : "l"(hp + 32 * j) : "memory");
    if (j < 4) kpv[3 * j] = x0; else vpv[3 * j - 10] = x0;
    if (j < 3) kpv[3 * j + 1] = x1; else vpv[3 * j - 9] = x1;
    if (j < 3) kpv[3 * j + 2] = x2; else if (j < 6) vpv[3 * j - 8] = x2;
  }
}

template <int ROT>
__device__ __forceinline__ void pack_qkv(const float* acc, uint32_t (&qlo)[10], uint32_t (&qhi)[10], uint32_t (&klo)[10],
                                         uint32_t (&khi)[10], uint32_t (&vlo)[10], uint32_t (&vhi)[10]) {
#pragma unroll
  for (int j = 0; j < 10; j++) {
    const int x = (j + ROT) % 10, tq = x < 8 ? x : 16 + x, tk = x < 8 ? 8 + x : 18 + x, tv = x < 8 ? 16 + x : 20 + x;
    khi[j] = pack2(acc[4 * tk + 2], acc[4 * tk + 3]);
    vhi[j] = movm(pack2(acc[4 * tv + 2], acc[4 * tv + 3]));
    qlo[j] = pack2(acc[4 * tq], acc[4 * tq + 1]);
    qhi[j] = pack2(acc[4 * tq + 2], acc[4 * tq + 3]);
    klo[j] = pack2(acc[4 * tk], acc[4 * tk + 1]);
    vlo[j] = pack2(acc[4 * tv], acc[4 * tv + 1]);
    asm volatile("" : "+r"(khi[j]), "+r"(qlo[j]), "+r"(qhi[j]), "+r"(klo[j]), "+r"(vlo[j]));
  }
}

template <int ROT> __device__ __forceinline__ void halo_send(const float* acc, uint4* ho, uint32_t tag) {
#pragma unroll
  for (int j = 0; j < 7; j++) {
    uint32_t x[3];
#pragma unroll
    for (int e = 0; e < 3; e++) {
      const int i = 3 * j + e, y = (i % 10 + ROT) % 10, tk = y < 8 ? 8 + y : 18 + y, tv = y < 8 ? 16 + y : 20 + y;
      x[e] = i < 10 ? pack2(acc[4 * tk + 2], acc[4 * tk + 3]) : i < 20 ? movm(pack2(acc[4 * tv + 2], acc[4 * tv + 3])) : 0u;
    }
    asm volatile("st.relaxed.gpu.global.v4.u32 [%0], {%1, %2, %3, %4};" ::"l"(ho + 32 * j), "r"(x[0]), "r"(x[1]), "r"(x[2]), "r"(tag) : "memory");
  }
}

__device__ __forceinline__ void attention(float* acc, uint32_t sb, int b, int par, int w, int lane, uint32_t tag) {
  const int g = lane >> 2, t = lane & 3;
  uint32_t klo[10], khi[10], vlo[10], vhi[10], qlo[10], qhi[10], kpv[10], vpv[10];
  if (HALO_FIRST && w == 3 && b < NCTA - 8) {
    uint4* ho = g_halo + (b * 2 + par) * 224 + lane;
    if (tail_first(b & 7)) halo_send<8>(acc, ho, tag);
    else halo_send<0>(acc, ho, tag);
    TSIF(par == 0, 76);
    pin<120>(acc);
  }
  if (tail_first(b & 7)) pack_qkv<8>(acc, qlo, qhi, klo, khi, vlo, vhi);
  else pack_qkv<0>(acc, qlo, qhi, klo, khi, vlo, vhi);
  const uint32_t xa = sb + OFF_KVX + (par * 3) * 2560 + lane * 16;
  if (w < 3) {
    sts128(xa + w * 2560, khi[0], khi[1], khi[2], khi[3]);
    sts128(xa + w * 2560 + 512, khi[4], khi[5], khi[6], khi[7]);
    sts128(xa + w * 2560 + 1024, khi[8], khi[9], vhi[0], vhi[1]);
    sts128(xa + w * 2560 + 1536, vhi[2], vhi[3], vhi[4], vhi[5]);
    sts128(xa + w * 2560 + 2048, vhi[6], vhi[7], vhi[8], vhi[9]);
  } else if (!HALO_FIRST && b < NCTA - 8) {
    uint4* ho = g_halo + (b * 2 + par) * 224 + lane;
#pragma unroll
    for (int j = 0; j < 7; j++) {
      const uint32_t x0 = j < 4 ? khi[3 * j] : vhi[3 * j - 10], x1 = j < 3 ? khi[3 * j + 1] : vhi[3 * j - 9];
      const uint32_t x2 = j < 3 ? khi[3 * j + 2] : j < 6 ? vhi[3 * j - 8] : 0u;
      asm volatile("st.relaxed.gpu.global.v4.u32 [%0], {%1, %2, %3, %4};" ::"l"(ho + 32 * j), "r"(x0), "r"(x1), "r"(x2), "r"(tag) : "memory");
    }
  }
  TSIF(par == 0 && w == 1, 64);
  TSIF(par == 0 && w == 3 && !HALO_FIRST, 76);
#pragma unroll
  for (int j = 0; j < 10; j++) vlo[j] = movm(vlo[j]);
  const bool far0 = 2 * t > g, far1 = 2 * t + 1 > g;
  const uint32_t mfar = (far0 ? 0x0000FFFFu : 0u) | (far1 ? 0xFFFF0000u : 0u);
  float slo[4][2], shi[4][2], lg[2][2];
  uint32_t phi[4], plo[4], qml[4], qmh[4];
#pragma unroll
  for (int h = 0; h < 4; h++) {
    const int f = h == 0 ? 0 : h == 1 ? 3 : h == 2 ? 5 : 8, hf = h < 2 ? 2 : 7;
    const bool mine = (h & 1) ? t >= 2 : t < 2;
    qml[h] = mine ? qlo[hf] : 0u;
    qmh[h] = mine ? qhi[hf] : 0u;
    float a[4] = {0.f, 0.f, 0.f, 0.f}, c[4] = {0.f, 0.f, 0.f, 0.f};
    mma16816(a, qlo[f], qhi[f], qlo[f + 1], qhi[f + 1], klo[f], klo[f + 1]);
    mma16816(c, qlo[f], qhi[f], qlo[f + 1], qhi[f + 1], khi[f], khi[f + 1]);
    mma1688(a, qml[h], qmh[h], klo[hf]);
    mma1688(c, qml[h], qmh[h], khi[hf]);
    slo[h][0] = a[0];
    slo[h][1] = a[1];
    shi[h][0] = lg[h & 1][0] = far0 ? a[2] : c[2];
    shi[h][1] = lg[h & 1][1] = far1 ? a[3] : c[3];
    if (!ATT_MERGE && (h & 1)) softmax_two(lg, phi[h - 1], phi[h]);
  }
  TSIF(par == 0 && w == 1, 65);
  wg_sync(1 + par);
  TSIF(par == 0 && w == 1, 66);
  const bool nohist = (w == 0) && (b < 8);
  const uint4* hp = g_halo + ((b - 8) * 2 + par) * 224 + lane;
  uint32_t tg[7];
  if (w > 0) {
    const uint4 v0 = lds128(xa + (w - 1) * 2560), v1 = lds128(xa + (w - 1) * 2560 + 512), v2 = lds128(xa + (w - 1) * 2560 + 1024);
    const uint4 v3 = lds128(xa + (w - 1) * 2560 + 1536), v4 = lds128(xa + (w - 1) * 2560 + 2048);
    kpv[0] = v0.x; kpv[1] = v0.y; kpv[2] = v0.z; kpv[3] = v0.w; kpv[4] = v1.x; kpv[5] = v1.y; kpv[6] = v1.z; kpv[7] = v1.w;
    kpv[8] = v2.x; kpv[9] = v2.y; vpv[0] = v2.z; vpv[1] = v2.w; vpv[2] = v3.x; vpv[3] = v3.y; vpv[4] = v3.z; vpv[5] = v3.w;
    vpv[6] = v4.x; vpv[7] = v4.y; vpv[8] = v4.z; vpv[9] = v4.w;
  } else if (nohist) {
#pragma unroll
    for (int j = 0; j < 10; j++) kpv[j] = vpv[j] = 0u;
  } else {
    TSIF(par == 0, 77);
    halo_read(kpv, vpv, tg, hp);
  }
  if (w == 0 && !nohist) {
    int spins = 0;
    while (true) {
      bool ok = true;
#pragma unroll
      for (int j = 0; j < 7; j++) ok = ok && tg[j] == tag;
      if (__all_sync(0xffffffffu, ok) || ++spins > SPIN_LIMIT) break;
      halo_read(kpv, vpv, tg, hp);
    }
    TSIF(par == 0, 79);
  }
#pragma unroll
  for (int h = 0; h < 4; h++) {
    const int f = h == 0 ? 0 : h == 1 ? 3 : h == 2 ? 5 : 8, hf = h < 2 ? 2 : 7;
    float a[4] = {0.f, 0.f, 0.f, 0.f};
    mma16816(a, qlo[f], qhi[f], qlo[f + 1], qhi[f + 1], kpv[f], kpv[f + 1]);
    mma1688(a, qml[h], qmh[h], kpv[hf]);
    const float ninf = __int_as_float(0xff800000);
    lg[h & 1][0] = far0 ? (nohist ? ninf : a[0]) : slo[h][0];
    lg[h & 1][1] = far1 ? (nohist ? ninf : a[1]) : slo[h][1];
    if (h & 1) {
      softmax_two(lg, plo[h - 1], plo[h]);
      if (ATT_MERGE) {
        const float lh[2][2] = {{shi[h - 1][0], shi[h - 1][1]}, {shi[h][0], shi[h][1]}};
        softmax_two(lh, phi[h - 1], phi[h]);
      }
    }
  }
  TSIF(par == 0 && w <= 1, 67 + w);
  uint32_t ov[20];
#pragma unroll
  for (int hp = 0; hp < 2; hp++) {
    const int hf = hp ? 7 : 2;
    float sh[4] = {0.f, 0.f, 0.f, 0.f}, i0 = 0.f, i1 = 0.f;
#pragma unroll
    for (int e = 0; e < 2; e++) {
      const int h = 2 * hp + e, f = h == 0 ? 0 : h == 1 ? 3 : h == 2 ? 5 : 8;
      const uint32_t a0 = plo[h] & mfar, a2 = plo[h] & ~mfar, a3 = phi[h] & mfar, c1 = phi[h] & ~mfar;
      float sum[4] = {0.f, 0.f, 0.f, 0.f};
      mma1688(sum, plo[h], phi[h], 0x3F803F80u);
      const float r0 = rcp(sum[0]), r1 = rcp(sum[2]);
#pragma unroll
      for (int j = f; j < f + 2; j++) {
        float o[4] = {0.f, 0.f, 0.f, 0.f};
        mma16816(o, a0, 0u, a2, a3, vpv[j], vlo[j]);
        mma1688(o, 0u, c1, vhi[j]);
        ov[2 * j] = pack2(o[0] * r0, o[1] * r0);
        ov[2 * j + 1] = pack2(o[2] * r1, o[3] * r1);
      }
      const bool mine = e ? g >= 4 : g < 4;
      mma16816(sh, a0, 0u, a2, a3, mine ? vpv[hf] : 0u, mine ? vlo[hf] : 0u);
      mma1688(sh, 0u, c1, mine ? vhi[hf] : 0u);
      if (e == 0 || t >= 2) {
        i0 = r0;
        i1 = r1;
      }
    }
    ov[2 * hf] = pack2(sh[0] * i0, sh[1] * i0);
    ov[2 * hf + 1] = pack2(sh[2] * i1, sh[3] * i1);
  }
  TS(32 + 4 * par + w);
  mbar_wait(sb + OFF_BAR + 8 * B_P1, 0);
  const uint32_t oa = sb + OFF_OA + (lane >> 4) * 2048 + (32 * w + 2 * (lane & 15) + par) * 16;
#pragma unroll
  for (int j = 0; j < 5; j++) stsm4(oa + 4096 * j, ov + 4 * j);
  TSIF(par == 0 && w == 0, 120);
  fence_async_smem();
  TSIF(par == 0 && w == 0, 121);
  __syncwarp();
  if (lane == 0) mbar_arrive(sb + OFF_BAR + 8 * B_ATTN);
  TSM(w == 0 || w == 2, 122 + par + (w == 2 ? 3 : 0));
}

struct Maps {
  CUtensorMap x, wm, wt, k, v, y, wo, qm, qt, om, ot, u;
};

__device__ __forceinline__ void load_stage(uint32_t sb, int kb, int b, const Maps& m) {
  const uint32_t st = sb + (kb & 3) * STAGE_BYTES, bar = sb + OFF_BAR + 8 * (B_FULL1 + (kb & 3));
  const int r = b >> 3, hg = b & 7, slab = kb - KV_KB;
  const bool kv = slab >= 0 && slab < 5;
  const uint32_t kbar = sb + OFF_BAR + 8 * (B_KV + slab), dst = sb + OFF_KVS + slab * KVS_BYTES;
  mbar_expect_tx(bar, STAGE_BYTES);
  if (kv) mbar_expect_tx(kbar, KVS_BYTES);
  tma_3d(st, &m.x, 64 * kb, 64 * r, 0, bar);
  if (kv && KV_MIX) tma_3d(dst, &m.k, 0, 32 * (b >> 1) - 3, 2 * slab + (b & 1), kbar);
  tma_3d(st + ST_W, &m.wm, 80 * hg + (tail_first(hg) ? 16 : 0), 64 * kb, 0, bar);
  if (kv && KV_MIX) tma_3d(dst + KVS_V, &m.v, 0, 32 * (b >> 1), 2 * slab + (b & 1), kbar);
  tma_3d(st + ST_WT, &m.wt, 80 * hg + (tail_first(hg) ? 0 : 64), 64 * kb, 0, bar);
  if (kv && !KV_MIX) tma_3d(dst, &m.k, 0, 32 * (b >> 1) - 3, 2 * slab + (b & 1), kbar);
  if (kv && !KV_MIX) tma_3d(dst + KVS_V, &m.v, 0, 32 * (b >> 1), 2 * slab + (b & 1), kbar);
}

__global__ void __launch_bounds__(NTHR, 1) fused_kernel(const __grid_constant__ Maps m, const Params p) {
  extern __shared__ __align__(1024) uint8_t smem[];
  const uint32_t sb = (uint32_t)__cvta_generic_to_shared(smem);
  const uint32_t bars = sb + OFF_BAR;
  const int tid = threadIdx.x, lane = tid & 31;
  int b = blockIdx.x;
  if (BMAP == 1) b = (((b & 63) >> 3) * 2 + (b & 1)) * 8 + (((b < 64 ? 0x6521 : 0x7430) >> (4 * ((b >> 1) & 3))) & 7);
  if (BMAP == 2) b = ((b & 63) >> 2) * 8 + (((b < 64 ? 0x6521 : 0x7430) >> (4 * (b & 3))) & 7);
  if (BMAP == 3) b = (((b & 63) >> 3) * 2 + (b & 1)) * 8 + (((b < 64 ? 0x7430 : 0x6521) >> (4 * ((b >> 1) & 3))) & 7);
  if (BMAP == 4) b = (((b >> 4) * 2 + (b & 1)) * 8) + ((b >> 1) & 7);
  if (BMAP == 5) b = 127 - b;
  const int r = b >> 3, hg = b & 7;

  if (tid == T_ISSUE) {
    TSM(true, 0);
#pragma unroll
    for (int i = 0; i < 4; i++) mbar_init(bars + 8 * (B_FULL1 + i), 1);
#pragma unroll
    for (int i = 0; i < 3; i++) mbar_init(bars + 8 * (B_KV + i), 1);
    fence_async_smem();
#pragma unroll 1
    for (int kb = 0; kb <= PRE2; kb++) load_stage(sb, kb, b, m);
  } else if (tid >= T_PF && tid < T_PF + 12) {
    tm_prefetch(&m.x + (tid - T_PF));
  } else if (tid == T_INIT) {
#pragma unroll
    for (int i = 0; i < 4; i++) mbar_init(bars + 8 * (B_EMPTY1 + i), 8);
#pragma unroll
    for (int i = 0; i < 8; i++) mbar_init(bars + 8 * (B_FULL2 + i), 1);
#pragma unroll
    for (int i = 0; i < 4; i++) mbar_init(bars + 8 * (B_EMPTY2 + i), 8);
#pragma unroll
    for (int i = 0; i < 4; i++) mbar_init(bars + 8 * (B_U + i), 1);
    mbar_init(bars + 8 * B_HA, 4);
    mbar_init(bars + 8 * B_GATE, 4);
    mbar_init(bars + 8 * B_HB, 1);
    mbar_init(bars + 8 * B_KVD, 4);
    mbar_init(bars + 8 * B_QF, 1);
    mbar_init(bars + 8 * B_ATTN, 8);
    mbar_init(bars + 8 * B_P1, 8);
    mbar_init(bars + 8 * B_C34, 1);
#pragma unroll
    for (int i = 0; i < 5; i++) mbar_init(bars + 8 * (B_YST + i), 4);
#pragma unroll
    for (int i = 0; i < 5; i++) mbar_init(bars + 8 * (B_US + i), 4);
    mbar_init(bars + 8 * B_YSIG, 1);
    mbar_init(bars + 8 * B_YFULL, 1);
    mbar_init(bars + 8 * B_EPOCH, 1);
    mbar_init(bars + 8 * B_PREP, 4);
    mbar_init(bars + 8 * B_USIG, 1);
    mbar_init(bars + 8 * B_WST, 1);
#pragma unroll
    for (int i = 3; i < 5; i++) mbar_init(bars + 8 * (B_KV + i), 1);
    mbar_init(bars + 8 * B_E3, 8);
    mbar_init(bars + 8 * B_LAST, 1);
    mbar_init(bars + 8 * B_OSIG, 1);
    mbar_init(bars + 8 * B_WOP, 1);
    fence_async_smem();
  }
  const int warp = __shfl_sync(0xffffffffu, tid >> 5, 0), wg = warp >> 2, w = warp & 3;
  __syncthreads();

  if (wg == 3) {
    asm volatile("setmaxnreg.dec.sync.aligned.u32 56;");
    if (w == 0) {
      if (lane == 0) {
#pragma unroll 1
        for (int kb = 1 + PRE2; kb < 10; kb++) {
          if (kb >= 4) mbar_wait(bars + 8 * (kb == 7 ? B_E3 : B_EMPTY1 + (kb & 3)), (kb >> 3) & 1);
          TSIF(kb >= 4, 44 + kb);
          load_stage(sb, kb, b, m);
          TSIF(kb == 3, 60);
          if (kb == TRIG_KB) mbar_arrive(bars + 8 * B_LAST);
        }
        mbar_wait(bars + 8 * B_WOP, 0);
        mbar_wait(bars + 8 * WL_TRIG, 0);
        mbar_wait(bars + 8 * B_EPOCH, 0);
        flag_wait(g_cnt + C_W + 32 * hg, (lds32(sb + OFF_EPOCH) + 1) * 16);
        TS(30);
#pragma unroll 1
        for (int j = 0; j < 8; j++) {
          if (j >= 6) mbar_wait(bars + 8 * (B_EMPTY2 + j - 6), 0);
          if (j == 4) mbar_wait(bars + 8 * B_ATTN, 0);
          TSIF(j >= 6, 100 + j);
          if (RF_GATE && j == 6) mbar_wait(bars + 8 * B_YSIG, 0);
          mbar_expect_tx(bars + 8 * (B_FULL2 + j), j == 0 ? WO_BYTES : j == 5 ? O_BYTES + WO_BYTES + 512 : O_BYTES + WO_BYTES);
          bulk_load(sb + off_w(j), g_WO + (hg * 8 + step_src(hg, j)) * 800, WO_BYTES, bars + 8 * (B_FULL2 + j));
        }
        mbar_wait(bars + 8 * (B_EMPTY2 + 3), 0);
        mbar_expect_tx(bars + 8 * B_QF, O_BYTES);
        tma_2d(sb + OFF_QS, &m.qm, 80 * hg, 128 * r, bars + 8 * B_QF);
        tma_2d(sb + OFF_QT, &m.qt, 80 * hg + 64, 128 * r, bars + 8 * B_QF);
      }
    } else if (w == 1) {
      unsigned epoch = 0;
      if (lane == 0) {
        epoch = atomicAdd(g_cnt + C_LAUNCH, 1u) / NCTA;
        asm volatile("st.shared.u32 [%0], %1;" ::"r"(sb + OFF_EPOCH), "r"(epoch) : "memory");
        mbar_arrive(bars + 8 * B_EPOCH);
        mbar_wait(bars + 8 * B_KVD, 0);
        mbar_expect_tx(bars + 8 * B_HB, 5 * 4096);
#pragma unroll 1
        for (int c = 0; c < 5; c++) {
          if (c == 3) mbar_wait(bars + 8 * B_S3, 0);
          bulk_load(sb + off_ch(c) + U_BYTES, p.ssm_k + (5 * b + c) * SEQ, 4096, bars + 8 * B_HB);
        }
#pragma unroll
        for (int c = 0; c < 4; c++) mbar_expect_tx(bars + 8 * (B_U + c), c < 3 ? U_BYTES : 2 * U_BYTES);
        const uint4* usrc = g_U + 5 * b * U_PITCH;
        mbar_wait(bars + 8 * B_USIG, 0);
        flag_wait(g_cnt + C_PREP + 32 * (b & 15), (epoch + 1) * NCTA);
        TS(23);
#pragma unroll
        for (int c = 0; c < 5; c++) {
          if (c == 3) mbar_wait(bars + 8 * (B_U + 2), 0);
          bulk_load(sb + off_ch(c), usrc + c * U_PITCH, U_BYTES, bars + 8 * (B_U + (c < 3 ? c : 3)));
          TSIF(c == 0 || c == 4, 116 + (c >> 2));
        }
      }
      epoch = __shfl_sync(0xffffffffu, epoch, 0);
      if (lane < 8) {
        const int src = (b & ~7) | step_src(hg, lane);
        mbar_wait(bars + 8 * B_OSIG, 0);
        TS(20);
        flag_wait(g_cnt + C_O + 32 * src, epoch + 1);
        if (lane >= 1 && lane < 4) bulk_load(sb + off_o(lane), g_O + src * 1280, O_BYTES, bars + 8 * (B_FULL2 + lane));
        __syncwarp(0xff);
        TS(21);
        if (lane == 5) bulk_load(sb + OFF_GATE, g_gate + 128 * r, 512, bars + 8 * (B_FULL2 + 5));
#pragma unroll 1
        for (int j = 4; j < 8; j++) {
          if (lane == j) {
            mbar_wait(bars + 8 * (j < 6 ? B_C34 : B_EMPTY2 + j - 6), 0);
            if (RF_GATE && j == 6) mbar_wait(bars + 8 * B_YSIG, 0);
            bulk_load(sb + off_o(j), g_O + src * 1280, O_BYTES, bars + 8 * (B_FULL2 + j));
          }
          __syncwarp(0xff);
        }
        TS(22);
      }
    } else if (w == 2) {
      mbar_wait(bars + 8 * B_PREP, 0);
      flag_signal(g_cnt + C_PREP, 16, lane);
      TS(25);
      if (lane == 0) mbar_arrive(bars + 8 * B_USIG);
      mbar_wait(bars + 8 * B_GATE, 0);
      if ((NOMB & 1) && lane == 0) asm volatile("fence.release.gpu;" ::: "memory");
      mbar_wait(bars + 8 * B_ATTN, 0);
      if (lane == 0) {
        if (O_DEFER) mbar_wait(bars + 8 * (B_U + 3), 0);
        asm volatile("cp.async.bulk.global.shared::cta.bulk_group [%0], [%1], 20480;\ncp.async.bulk.commit_group;\n"
                     "cp.async.bulk.wait_group 0;\nfence.proxy.async.global;" ::"l"(g_O + b * 1280), "r"(sb + OFF_OA) : "memory");
      }
      TS(74);
      if (!(NOMB & 1)) flag_signal(g_cnt + C_O + 32 * b, 1, lane);
      else if (lane == 0) flag_bump(g_cnt + C_O + 32 * b);
      TS(26);
      if (lane == 0) mbar_arrive(bars + 8 * B_OSIG);

    } else {
      if (lane == 0) {
        uint4* dst = g_WO + (hg * 8 + (r >> 1)) * 800 + (r & 1) * 80;
        mbar_wait(bars + 8 * B_P1, 0);
        mbar_wait(bars + 8 * WB_TRIG, 0);
        mbar_expect_tx(bars + 8 * B_WST, WO_BYTES / 2);
        tma_3d(sb + OFF_WS, &m.wo, 0, 40 * r, 5 * hg, bars + 8 * B_WST);
        mbar_wait(bars + 8 * B_WST, 0);
        mbar_wait(bars + 8 * WO_TRIG, 0);
#pragma unroll 1
        for (int n = 0; n < 5; n++)
          asm volatile("cp.async.bulk.global.shared::cta.bulk_group [%0], [%1], 1280;" ::"l"(dst + 160 * n), "r"(sb + OFF_WS + 1280 * n) : "memory");
        asm volatile("cp.async.bulk.commit_group;\ncp.async.bulk.wait_group 0;\nfence.proxy.async.global;" ::: "memory");
        if (!(NOMB & 4)) asm volatile("fence.release.gpu;" ::: "memory");
        flag_bump(g_cnt + C_W + 32 * hg);
        mbar_arrive(bars + 8 * B_WOP);
        TS(71);
#pragma unroll 1
        for (int c = 0; c < 5; c++) {
          mbar_wait(bars + 8 * (B_YST + c), 0);
          asm volatile("cp.async.bulk.global.shared::cta.bulk_group [%0], [%1], 4096;\ncp.async.bulk.commit_group;"
                       ::"l"(g_Y + (5 * b + c) * Y_PITCH), "r"(sb + off_ch(c)) : "memory");
          if (c == 2) {
            asm volatile("cp.async.bulk.wait_group.read 0;" ::: "memory");
            mbar_arrive(bars + 8 * B_C34);
          }
        }
        asm volatile("cp.async.bulk.wait_group 0;\nfence.proxy.async.global;" ::: "memory");
        TS(75);
        if (!(NOMB & 2)) asm volatile("fence.release.gpu;" ::: "memory");
        flag_bump(g_cnt + C_Y + 32 * (b >> 4));
        TS(27);
        mbar_arrive(bars + 8 * B_YSIG);
        mbar_expect_tx(bars + 8 * B_YFULL, 20480);
        flag_wait(g_cnt + C_Y + 32 * hg, (lds32(sb + OFF_EPOCH) + 1) * 16);
        TS(24);
        tma_2d(sb + OFF_YT, &m.y, 128 * r, 80 * hg, bars + 8 * B_YFULL);
        tma_2d(sb + OFF_YT + 10240, &m.y, 128 * r + 64, 80 * hg, bars + 8 * B_YFULL);
      }
    }
  } else {
    asm volatile("setmaxnreg.inc.sync.aligned.u32 152;");
    if (wg < 2) {
      float acc[120];
#pragma unroll
      for (int i = 0; i < 120; i++) acc[i] = 0.f;
      const uint32_t da = desc_lo(sb + wg * 8192, 16), db = desc_lo(sb + ST_W, 8192), dc = desc_lo(sb + ST_WT, 2048);
      if (PW1) pin<120>(acc);
      if (PW1 == 2) mbar_wait(bars + 8 * B_FULL1, 0);
#pragma unroll 1
      for (int kb = 0; kb < 10; kb++) {
        mbar_wait(bars + 8 * (B_FULL1 + (kb & 3)), (kb >> 2) & 1);
        const uint32_t so = (kb & 3) * (STAGE_BYTES >> 4);
        wg_fence();
#pragma unroll
        for (int k = 0; k < 4; k++) {
          WgSST<192>::mma<HI_SW128, HI_SW128>(acc, da + so + 2 * k, db + so + 128 * k, 1);
          WgSST<48>::mma<HI_SW128, HI_SW32>(acc + 96, da + so + 2 * k, dc + so + 32 * k, 1);
        }
        wg_commit();
        wg_wait<1>();
        if (kb > 0 && lane == 0) mbar_arrive(bars + 8 * (kb == 4 ? B_E3 : B_EMPTY1 + ((kb - 1) & 3)));
      }
      mbar_wait(bars + 8 * B_EPOCH, 0);
      const uint32_t tag = lds32(sb + OFF_EPOCH) + 1;
      mbar_wait(bars + 8 * B_S3, 0);
      wg_wait<0>();
      pin<120>(acc);
      if (lane == 0) mbar_arrive(bars + 8 * B_P1);
      TSM(w == 0, 3 + wg);
      attention(acc, sb, b, wg, w, lane, tag);
    } else {
      const int tw = tid & 127, chl = 64 * (b & 1) + 8 * w + (lane >> 2);
      uint4* up = g_U + chl * U_PITCH + ((4 * (b >> 1) + (lane & 3)) ^ ((b >> 2) & 1));
      uint2 sw[10];
      uint32_t dv = 0;
      if (lane < 5) dv = __ldg(reinterpret_cast<const unsigned short*>(p.ssm_D) + 5 * b + lane);
#pragma unroll
      for (int i = 0; i < 10; i++) sw[i] = ldg64(reinterpret_cast<const uint2*>(p.shift_k) + chl + 128 * (i >> 1) + 32 * (i & 1));
      uint32_t tab[12];
      fft_tables(tab, tw);
      uint4 res[10];
#pragma unroll
      for (int i = 0; i < 10; i++) res[i] = make_uint4(0, 0, 0, 0);
#pragma unroll 1
      for (int slab = 0; slab < 5; slab++) {
#pragma unroll
        for (int i = 0; i < 8; i++) res[i] = res[i + 2];
        prep_slab(res + 8, sw, sb, slab, w, lane);
        TSIF(w == 0, 99 + 4 * slab);
#pragma unroll
        for (int i = 0; i < 8; i++) sw[i] = sw[i + 2];
      }
      TSIF(w == 0, 28);
      __syncwarp();
      if (lane == 0) mbar_arrive(bars + 8 * B_KVD + ((res[8].x ^ res[9].x) & p.zero));
      mbar_wait(bars + 8 * B_KVD, 0);
      fft_tables_store(tab, sb, tw);
      mbar_wait(bars + 8 * B_LAST, 0);
#pragma unroll
      for (int i = 0; i < 10; i++) up[(128 * (i >> 1) + 32 * (i & 1)) * U_PITCH] = res[i];
      __syncwarp();
      if (lane == 0) mbar_arrive(bars + 8 * B_PREP);
      TSIF(w == 0 && !U_TMA, 5);
      mbar_wait(bars + 8 * (G_AFTER ? B_USIG : B_LAST), 0);
      prep_gate(p, b, w, lane);
      __syncwarp();
      if (lane == 0) mbar_arrive(bars + 8 * B_GATE);
      TSIF(w == 0, 72);
      mbar_wait(bars + 8 * B_HB, 0);
      TSIF(w == 0, 2);
      const uint32_t ha = sb + U_BYTES + ((tw >> 3) * 16 + 8 + (tw & 7)) * 16;
      uint4 hv[5];
#pragma unroll
      for (int c = 0; c < 5; c++) hv[c] = lds128(ha + off_ch(c));
      __syncwarp();
#pragma unroll
      for (int c = 0; c < 5; c++) sts128((ha ^ 16) + off_ch(c), hv[c].x, hv[c].y, hv[c].z, hv[c].w);
      if (tw < 5) asm volatile("st.shared.f32 [%0], %1;" ::"r"(sb + OFF_D + 4 * tw), "f"(bf_lo(dv) * 0.125f) : "memory");
      fence_async_smem();
      __syncwarp();
      if (lane == 0) mbar_arrive(bars + 8 * B_HA);
      TSIF(w == 0, 6);
    }

    FftConst fc;
    fft_twiddles(fc, w, lane);
    TSM(w == 0 && wg == 0, 104);
    mbar_wait(bars + 8 * B_HA, 0);
    fft_matrices(fc, sb, w, lane);
    TSM(w == 0 && wg == 0, 105);
    if (ATT_GATE && !H_EARLY) mbar_wait(bars + 8 * B_ATTN, 0);
    TSM(w == 0 && wg == 2, 124);
#pragma unroll 1
    for (int c = wg == 2 ? 0 : wg + 1; c < 5; c += !CH_W2 ? 3 : wg < 2 ? 5 : c ? 1 : 3) {
      conv_channel(fc, sb, c, wg, w, lane);
      if (lane == 0) mbar_arrive(bars + 8 * (B_YST + c));
      TSM(w == 0, 10 + c);
    }

    if (wg < 2) {
      const int g = lane >> 2;
      float acc[40];
#pragma unroll
      for (int i = 0; i < 40; i++) acc[i] = 0.f;
      const uint32_t da = desc_lo(sb + wg * 1024, 2048), db = desc_lo(sb, 2560);
      mbar_wait(bars + 8 * B_ATTN, 0);
      mbar_wait(bars + 8 * (B_YST + 3), 0);
      mbar_wait(bars + 8 * (B_YST + 4), 0);
      if (PW2) mbar_wait(bars + 8 * B_FULL2, 0);
      TSM(w == 0, 15 + wg);
#pragma unroll 1
      for (int j = 0; j < 8; j++) {
        mbar_wait(bars + 8 * (B_FULL2 + j), 0);
        const uint32_t oa = da + (off_o(j) >> 4), ob = db + (off_w(j) >> 4);
        wg_fence();
#pragma unroll
        for (int k = 0; k < 5; k++) WgSST<80>::mma<HI_NONE, HI_SW32>(acc, oa + 256 * k, ob + 32 * k, 1);
        wg_commit();
        wg_wait<1>();
        if (j >= 1 && j <= 4 && lane == 0) mbar_arrive(bars + 8 * (B_EMPTY2 + j - 1));
      }
      TSIF(w == 0 && wg == 0, 113);
      const int tr = 64 * wg + 16 * w + (lane & 15);
      const uint32_t fm = sb + OFF_QS + tr * 128, fx = (lane >> 4) ^ (tr & 7);
      const uint32_t ft = sb + OFF_QT + tr * 32 + (((lane >> 4) ^ (tr >> 2)) & 1) * 16;
      const float g0 = __uint_as_float(lds32(sb + OFF_GATE + (64 * wg + 16 * w + g) * 4));
      const float g1 = __uint_as_float(lds32(sb + OFF_GATE + (64 * wg + 16 * w + 8 + g) * 4));
      const uint32_t ga = pack2(g0, g0), gb = pack2(g1, g1);
      const uint32_t na = pack2(1.f - g0, 1.f - g0), nb = pack2(1.f - g1, 1.f - g1);

      wg_wait<0>();
      pin<40>(acc);
      TSM(w == 0, 17 + wg);
      uint32_t pb[20];
#pragma unroll
      for (int j = 0; j < 10; j++) {
        pb[2 * j] = bmul(na, pack2(acc[4 * j], acc[4 * j + 1]));
        pb[2 * j + 1] = bmul(nb, pack2(acc[4 * j + 2], acc[4 * j + 3]));
        asm volatile("" : "+r"(pb[2 * j]), "+r"(pb[2 * j + 1]));
      }
      const uint32_t ya = sb + OFF_YT + wg * 10240 + ((lane >> 4) * 8 + (lane & 7)) * 128 +
                          (((2 * w + (((lane >> 3) & 1) ^ wg)) ^ (lane & 7)) << 4);
      uint32_t qf[20];
      mbar_wait(bars + 8 * B_QF, 0);
#pragma unroll
      for (int j = 0; j < 5; j++) ldsm4(qf + 4 * j, j < 4 ? fm + ((fx ^ (2 * j)) << 4) : ft);
      mbar_wait(bars + 8 * B_YFULL, 0);
      TSM(w == 0 && wg == 0, 19);
#pragma unroll
      for (int j = 0; j < 5; j++) {
        uint32_t y[4];
        ldsm4t(y, ya + 2048 * j);
#pragma unroll
        for (int i = 0; i < 4; i++) qf[4 * j + i] = badd(bmul((i & 1) ? gb : ga, bmul(qf[4 * j + i], y[i])), pb[4 * j + i]);
      }
#pragma unroll
      for (int j = 0; j < 5; j++) stsm4(j < 4 ? fm + ((fx ^ (2 * j)) << 4) : ft, qf + 4 * j);
      fence_async_smem();
      __syncwarp();
      if (lane == 0) {
        const int row = 64 * wg + 16 * w;
        asm volatile("cp.async.bulk.tensor.2d.global.shared::cta.bulk_group [%0, {%2, %3}], [%1];"
                     ::"l"(&m.om), "r"(sb + OFF_QS + row * 128), "r"(80 * hg), "r"(128 * r + row) : "memory");
        asm volatile("cp.async.bulk.tensor.2d.global.shared::cta.bulk_group [%0, {%2, %3}], [%1];"
                     ::"l"(&m.ot), "r"(sb + OFF_QT + row * 32), "r"(80 * hg + 64), "r"(128 * r + row) : "memory");
        asm volatile("cp.async.bulk.commit_group;\ncp.async.bulk.wait_group.read 0;" ::: "memory");
      }
      TSM(true, 40 + 4 * wg + w);
      if (ENDBAR) asm volatile("bar.sync 15, 256;" ::: "memory");
    }
  }
}

typedef CUresult (*EncodeFn)(CUtensorMap*, CUtensorMapDataType, cuuint32_t, void*, const cuuint64_t*, const cuuint64_t*,
                             const cuuint32_t*, const cuuint32_t*, CUtensorMapInterleave, CUtensorMapSwizzle,
                             CUtensorMapL2promotion, CUtensorMapFloatOOBfill);

void encode(EncodeFn fn, CUtensorMap* tm, const void* base, int rank, const cuuint64_t* dims, const cuuint64_t* strides,
            const cuuint32_t* box, CUtensorMapSwizzle swz) {
  const cuuint32_t ones[3] = {1, 1, 1};
  fn(tm, CU_TENSOR_MAP_DATA_TYPE_BFLOAT16, rank, const_cast<void*>(base), dims, strides, box, ones,
     CU_TENSOR_MAP_INTERLEAVE_NONE, swz, CU_TENSOR_MAP_L2_PROMOTION_L2_128B, CU_TENSOR_MAP_FLOAT_OOB_FILL_NONE);
}

}

extern "C" void kernel_launch(void* const* d_in, const int* in_sizes, int n_in, void* d_out, int out_size) {
  (void)in_sizes; (void)n_in; (void)out_size;
  Params p;
  p.q = (const __nv_bfloat16*)d_in[0];
  p.k = (const __nv_bfloat16*)d_in[1];
  p.v = (const __nv_bfloat16*)d_in[2];
  p.shift_k = (const __nv_bfloat16*)d_in[3];
  p.ssm_k = (const __nv_bfloat16*)d_in[4];
  p.ssm_D = (const __nv_bfloat16*)d_in[5];
  p.wqkv = (const __nv_bfloat16*)d_in[7];
  p.wo = (const __nv_bfloat16*)d_in[8];
  p.gate_w = (const __nv_bfloat16*)d_in[9];
  p.out = (__nv_bfloat16*)d_out;
  p.zero = 0;

  static EncodeFn fn = nullptr;
  static void *yaddr = nullptr, *uaddr = nullptr;
  if (!fn) {
    cudaDriverEntryPointQueryResult qr;
    void* f = nullptr;
    cudaGetDriverEntryPoint("cuTensorMapEncodeTiled", &f, cudaEnableDefault, &qr);
    fn = (EncodeFn)f;
    cudaGetSymbolAddress(&yaddr, g_Y);
    cudaGetSymbolAddress(&uaddr, g_U);
    cudaFuncSetAttribute(fused_kernel, cudaFuncAttributeMaxDynamicSharedMemorySize, SMEM_BYTES);
  }
  Maps m;
  {
    const cuuint64_t dims[3] = {640, 1024, 2}, st[2] = {2560, 1280};
    const cuuint32_t box[3] = {64, 64, 2};
    encode(fn, &m.x, p.q, 3, dims, st, box, CU_TENSOR_MAP_SWIZZLE_128B);
  }
  {
    const cuuint64_t dims[3] = {640, 640, 3}, st[2] = {3840, 1280};
    const cuuint32_t box[3] = {64, 64, 3}, boxt[3] = {16, 64, 3};
    encode(fn, &m.wm, p.wqkv, 3, dims, st, box, CU_TENSOR_MAP_SWIZZLE_128B);
    encode(fn, &m.wt, p.wqkv, 3, dims, st, boxt, CU_TENSOR_MAP_SWIZZLE_32B);
  }
  {
    const cuuint64_t dims[3] = {64, 2048, 10}, st[2] = {1280, 128};
    const cuuint32_t boxk[3] = {64, 35, 1}, boxv[3] = {64, 32, 1};
    encode(fn, &m.k, p.k, 3, dims, st, boxk, CU_TENSOR_MAP_SWIZZLE_128B);
    encode(fn, &m.v, p.v, 3, dims, st, boxv, CU_TENSOR_MAP_SWIZZLE_128B);
  }
  {
    const cuuint64_t dims[3] = {16, 640, 40}, st[2] = {1280, 32};
    const cuuint32_t box[3] = {16, 40, 5};
    encode(fn, &m.wo, p.wo, 3, dims, st, box, CU_TENSOR_MAP_SWIZZLE_32B);
  }
  {
    const cuuint64_t dims[2] = {2048, 640}, st[1] = {Y_PITCH * 16};
    const cuuint32_t box[2] = {64, 80};
    encode(fn, &m.y, yaddr, 2, dims, st, box, CU_TENSOR_MAP_SWIZZLE_128B);
    const cuuint64_t stu[1] = {U_PITCH * 16};
    const cuuint32_t boxu[2] = {32, 64};
    encode(fn, &m.u, uaddr, 2, dims, stu, boxu, CU_TENSOR_MAP_SWIZZLE_NONE);
  }
  {
    const cuuint64_t dims[2] = {640, 2048}, st[1] = {1280};
    const cuuint32_t bqm[2] = {64, 128}, bqt[2] = {16, 128}, bom[2] = {64, 16}, bot[2] = {16, 16};
    encode(fn, &m.qm, p.q, 2, dims, st, bqm, CU_TENSOR_MAP_SWIZZLE_128B);
    encode(fn, &m.qt, p.q, 2, dims, st, bqt, CU_TENSOR_MAP_SWIZZLE_32B);
    encode(fn, &m.om, p.out, 2, dims, st, bom, CU_TENSOR_MAP_SWIZZLE_128B);
    encode(fn, &m.ot, p.out, 2, dims, st, bot, CU_TENSOR_MAP_SWIZZLE_32B);
  }
  fused_kernel<<<NCTA, NTHR, SMEM_BYTES>>>(m, p);
}
```

```cpp
#include <cuda.h>
#include <cuda_bf16.h>
#include <cuda_runtime.h>
#include <stdint.h>

namespace {

constexpr int SEQ = 2048, DIM = 640, NCTA = 128, NTHR = 512;

#define TRIG_KB 9
#define KV_KB 2
#define DEV_EXIT 0
#define ATT_GATE 1
#define G_AFTER 0
#define FENCE_LO 0
#define FENCE_HI 0
#define PW1 2
#define PW2 1
#define ENDBAR 0
#define PAD_KB 0
#define Y_ALIAS 1
#define H_EARLY 1
#define NOMB 0
#define SRC_ROT 0
#define WAIT_NS 0
#define WB_TRIG B_USIG
#define G_POS 0
#define TAILF 1
#define T_ISSUE 384
#define T_PF 416
#define T_INIT 448
#define ATT_MERGE 0
#define BMAP 1
#define PRE2 1
#define KV_MIX 0
#define O_DEFER 0
#define CH_W2 0
#define HALO_FIRST 1
#define PREV_EARLY 0
#define ACQ 0
#define U_TMA 0
#define U_GATE 0
#define RF_GATE 0
#define WO_TRIG B_WST
#define WL_TRIG B_WOP
#define WO_GATE 1

constexpr uint32_t STAGE_BYTES = 47104, ST_W = 16384, ST_WT = 40960;
constexpr uint32_t O_BYTES = 20480, WO_BYTES = 12800;
constexpr uint32_t OFF_OA = 0;
constexpr uint32_t OFF_QS = 3 * O_BYTES, OFF_QT = OFF_QS + 16384;
constexpr uint32_t OFF_WC = 81920;
constexpr uint32_t OFF_WA = 94720;
constexpr uint32_t OFF_GATE = 145920;
constexpr uint32_t OFF_TT = 146432;
constexpr uint32_t OFF_KVX = 148480;
constexpr uint32_t OFF_CH3 = 163840;
constexpr uint32_t CH_BYTES = 12288, U_BYTES = 4096;
constexpr uint32_t OFF_FT = 225280, OFF_GT = 229376;
constexpr uint32_t OFF_CH0 = 188416;
constexpr uint32_t OFF_KVS = OFF_CH0, KVS_V = 4480, KVS_BYTES = 8576;
constexpr uint32_t OFF_WS = OFF_WA;
__device__ __forceinline__ uint32_t off_us(int s) { return OFF_CH0 + 4096 * ((0x65320 >> (4 * s)) & 7); }
constexpr uint32_t OFF_YT = 163840;
constexpr uint32_t OFF_BAR = 231936;
constexpr uint32_t SMEM_BYTES = OFF_BAR + 512;

enum : uint32_t {
  B_FULL1 = 0, B_EMPTY1 = 4, B_S3 = 7, B_FULL2 = 52, B_EMPTY2 = 13, B_U = 8, B_GATE = 12, B_HA = 19, B_HB = 20,
  B_ATTN = 21, B_C34 = 22, B_CONV = 23, B_YFULL = 24, B_EPOCH = 25, B_PREP = 26, B_P1 = 27, B_LAST = 28,
  B_E3 = 29, B_OSIG = 30, B_WOP = 31, B_USIG = 32, B_WST = 33, B_KV = 34, B_KVD = 39, B_QF = 17, B_YST = 40,
  B_US = 45, B_YSIG = 50
};
constexpr uint32_t OFF_EPOCH = OFF_BAR + 8 * 51, OFF_D = OFF_BAR + 8 * 60;
__device__ __forceinline__ uint32_t off_o(int j) { return j < 4 ? OFF_OA + j * O_BYTES : j < 6 ? OFF_CH0 + (j - 4) * O_BYTES : OFF_OA + (j - 6) * O_BYTES; }
__device__ __forceinline__ uint32_t off_w(int j) { return j < 4 ? OFF_WA + j * WO_BYTES : j == 4 ? OFF_KVX : j == 5 ? OFF_WC : OFF_WA + (j - 6) * WO_BYTES; }
__device__ __forceinline__ int step_src(int hg, int j) { return SRC_ROT ? (hg + j) & 7 : j == 0 ? hg : j <= hg ? j - 1 : j; }
__device__ __forceinline__ bool tail_first(int hg) { return TAILF && (hg & 3) == 3; }
__device__ __forceinline__ uint32_t off_ch(int c) { return (c < 3 ? OFF_CH0 : OFF_CH3 - 3 * CH_BYTES) + c * CH_BYTES; }

#define U_PITCH 264
__device__ __align__(1024) uint4 g_U[DIM * U_PITCH];
__device__ uint4 g_O[NCTA * 1280];
#define g_Y g_U
constexpr int Y_PITCH = U_PITCH;
__device__ uint4 g_WO[64 * 800];
__device__ uint4 g_halo[NCTA * 2 * 7 * 32];
__device__ float g_gate[SEQ + PAD_KB * 256];
__device__ unsigned g_cnt[32 * (1 + 2 * 16 + 8 + NCTA)];
constexpr int C_LAUNCH = 0, C_PREP = 32, C_Y = 32 * 17, C_W = 32 * 33, C_O = 32 * 41;

#define TSM(cond, slot) do { } while (0)
#define TSIF(cond, slot) do { if (__LINE__ >= FENCE_LO && __LINE__ < FENCE_HI) sched_fence(); } while (0)
__device__ __forceinline__ void sched_fence() {
  asm volatile("{\n.reg .pred p;\n.reg .u32 c;\nmov.u32 c, %%clock;\nsetp.eq.u32 p, c, 0;\n@p st.shared.u32 [%0], c;\n}"
               ::"r"(1024 + OFF_EPOCH + 4) : "memory");
}
#define TS(slot) TSIF(true, slot)

struct Params {
  const __nv_bfloat16 *q, *k, *v, *shift_k, *ssm_k, *ssm_D, *wqkv, *wo, *gate_w;
  __nv_bfloat16* out;
  uint32_t zero;
};

#define POLL_NS 0
constexpr int SPIN_LIMIT = 1 << 17;

__device__ __forceinline__ void mbar_init(uint32_t bar, uint32_t count) {
  asm volatile("mbarrier.init.shared::cta.b64 [%0], %1;" ::"r"(bar), "r"(count) : "memory");
}
__device__ __forceinline__ void mbar_expect_tx(uint32_t bar, uint32_t bytes) {
  asm volatile("mbarrier.arrive.expect_tx.shared::cta.b64 _, [%0], %1;" ::"r"(bar), "r"(bytes) : "memory");
}
__device__ __forceinline__ void mbar_arrive(uint32_t bar) {
  asm volatile("mbarrier.arrive.shared::cta.b64 _, [%0];" ::"r"(bar) : "memory");
}
__device__ __forceinline__ void mbar_wait(uint32_t bar, uint32_t parity) {
  uint32_t ok;
  int spins = 0;
  do {
    if (WAIT_NS)
      asm volatile("{\n.reg .pred p;\nmbarrier.try_wait.parity.shared::cta.b64 p, [%1], %2, %3;\nselp.b32 %0, 1, 0, p;\n}"
                   : "=r"(ok) : "r"(bar), "r"(parity), "r"(WAIT_NS) : "memory");
    else
      asm volatile("{\n.reg .pred p;\nmbarrier.try_wait.parity.shared::cta.b64 p, [%1], %2;\nselp.b32 %0, 1, 0, p;\n}"
                   : "=r"(ok) : "r"(bar), "r"(parity) : "memory");
    if (++spins > SPIN_LIMIT) break;
  } while (!ok);
}
__device__ __forceinline__ void flag_poll(const unsigned* p, unsigned target) {
  unsigned v;
  int spins = 0;
  do {
    if (POLL_NS && spins) __nanosleep(POLL_NS);
    asm volatile("ld.relaxed.gpu.global.u32 %0, [%1];" : "=r"(v) : "l"(p) : "memory");
    if (++spins > SPIN_LIMIT) break;
  } while ((int)(v - target) < 0);
}
__device__ __forceinline__ void flag_wait(const unsigned* p, unsigned target) {
  flag_poll(p, target);
  if (ACQ) asm volatile("fence.acquire.gpu;\nfence.proxy.async.global;" ::: "memory");
}
__device__ __forceinline__ void flag_signal(unsigned* p, int n, int lane) {
  if (lane == 0) asm volatile("fence.release.gpu;" ::: "memory");
  __syncwarp();
  if (lane < n) asm volatile("red.relaxed.gpu.global.add.u32 [%0], 1;" ::"l"(p + 32 * lane) : "memory");
}
__device__ __forceinline__ void flag_bump(unsigned* p) {
  asm volatile("red.relaxed.gpu.global.add.u32 [%0], 1;" ::"l"(p) : "memory");
}
__device__ __forceinline__ void fence_async_smem() { asm volatile("fence.proxy.async.shared::cta;" ::: "memory"); }
__device__ __forceinline__ void wg_sync(int id) { asm volatile("bar.sync %0, 128;" ::"r"(id) : "memory"); }

__device__ __forceinline__ void tma_2d(uint32_t dst, const CUtensorMap* tm, int c0, int c1, uint32_t bar) {
  asm volatile("cp.async.bulk.tensor.2d.shared::cluster.global.mbarrier::complete_tx::bytes [%0], [%1, {%3, %4}], [%2];"
               ::"r"(dst), "l"(tm), "r"(bar), "r"(c0), "r"(c1) : "memory");
}
__device__ __forceinline__ void tma_3d(uint32_t dst, const CUtensorMap* tm, int c0, int c1, int c2, uint32_t bar) {
  asm volatile("cp.async.bulk.tensor.3d.shared::cluster.global.mbarrier::complete_tx::bytes [%0], [%1, {%3, %4, %5}], [%2];"
               ::"r"(dst), "l"(tm), "r"(bar), "r"(c0), "r"(c1), "r"(c2) : "memory");
}
__device__ __forceinline__ void bulk_load(uint32_t dst, const void* src, uint32_t bytes, uint32_t bar) {
  asm volatile("cp.async.bulk.shared::cluster.global.mbarrier::complete_tx::bytes [%0], [%1], %2, [%3];"
               ::"r"(dst), "l"(src), "r"(bytes), "r"(bar) : "memory");
}
__device__ __forceinline__ void tm_prefetch(const CUtensorMap* tm) {
  asm volatile("prefetch.tensormap [%0];" ::"l"(tm) : "memory");
}

__device__ __forceinline__ void wg_fence() { asm volatile("wgmma.fence.sync.aligned;" ::: "memory"); }
__device__ __forceinline__ void wg_commit() { asm volatile("wgmma.commit_group.sync.aligned;" ::: "memory"); }
template <int N> __device__ __forceinline__ void wg_wait() { asm volatile("wgmma.wait_group.sync.aligned %0;" ::"n"(N) : "memory"); }
__device__ __forceinline__ uint32_t desc_lo(uint32_t addr, uint32_t lbo) { return ((addr & 0x3FFFF) >> 4) | ((lbo >> 4) << 16); }
constexpr uint32_t desc_hi(uint32_t sbo, uint32_t swz) { return (sbo >> 4) | (swz << 30); }
constexpr uint32_t HI_SW128 = desc_hi(1024, 1), HI_SW64 = desc_hi(512, 2), HI_SW32 = desc_hi(256, 3), HI_NONE = desc_hi(128, 0);
template <int N> __device__ __forceinline__ void pin(float* d) {
#pragma unroll
  for (int i = 0; i < N; i++) asm volatile("" : "+f"(d[i])::"memory");
}

__device__ __forceinline__ uint32_t lds32(uint32_t a) {
  uint32_t v;
  asm volatile("ld.volatile.shared.u32 %0, [%1];" : "=r"(v) : "r"(a) : "memory");
  return v;
}
__device__ __forceinline__ uint4 ldg128(const void* a) {
  uint4 v;
  asm volatile("ld.global.nc.v4.u32 {%0, %1, %2, %3}, [%4];" : "=r"(v.x), "=r"(v.y), "=r"(v.z), "=r"(v.w) : "l"(a) : "memory");
  return v;
}
__device__ __forceinline__ uint2 ldg64(const void* a) {
  uint2 v;
  asm volatile("ld.global.nc.v2.u32 {%0, %1}, [%2];" : "=r"(v.x), "=r"(v.y) : "l"(a) : "memory");
  return v;
}
__device__ __forceinline__ void ldsm4(uint32_t* r, uint32_t a) {
  asm volatile("ldmatrix.sync.aligned.m8n8.x4.shared.b16 {%0, %1, %2, %3}, [%4];"
               : "=r"(r[0]), "=r"(r[1]), "=r"(r[2]), "=r"(r[3]) : "r"(a) : "memory");
}
__device__ __forceinline__ void ldsm4t(uint32_t* r, uint32_t a) {
  asm volatile("ldmatrix.sync.aligned.m8n8.x4.trans.shared.b16 {%0, %1, %2, %3}, [%4];"
               : "=r"(r[0]), "=r"(r[1]), "=r"(r[2]), "=r"(r[3]) : "r"(a) : "memory");
}
__device__ __forceinline__ uint4 lds128(uint32_t a) {
  uint4 v;
  asm volatile("ld.shared.v4.u32 {%0, %1, %2, %3}, [%4];" : "=r"(v.x), "=r"(v.y), "=r"(v.z), "=r"(v.w) : "r"(a) : "memory");
  return v;
}
__device__ __forceinline__ void sts128(uint32_t a, uint32_t x, uint32_t y, uint32_t z, uint32_t w) {
  asm volatile("st.shared.v4.u32 [%0], {%1, %2, %3, %4};" ::"r"(a), "r"(x), "r"(y), "r"(z), "r"(w) : "memory");
}
__device__ __forceinline__ void stsm4(uint32_t a, const uint32_t* r) {
  asm volatile("stmatrix.sync.aligned.m8n8.x4.shared.b16 [%0], {%1, %2, %3, %4};" ::"r"(a), "r"(r[0]), "r"(r[1]), "r"(r[2]), "r"(r[3]) : "memory");
}
__device__ __forceinline__ void stsm4t(uint32_t a, const uint32_t* r) {
  asm volatile("stmatrix.sync.aligned.m8n8.x4.trans.shared.b16 [%0], {%1, %2, %3, %4};" ::"r"(a), "r"(r[0]), "r"(r[1]), "r"(r[2]), "r"(r[3]) : "memory");
}
__device__ __forceinline__ uint32_t pack2(float lo, float hi) {
  uint32_t r;
  asm("cvt.rn.bf16x2.f32 %0, %1, %2;" : "=r"(r) : "f"(hi), "f"(lo));
  return r;
}
__device__ __forceinline__ uint32_t movm(uint32_t a) {
  uint32_t d;
  asm volatile("movmatrix.sync.aligned.m8n8.trans.b16 %0, %1;" : "=r"(d) : "r"(a));
  return d;
}
__device__ __forceinline__ uint32_t bmul(uint32_t a, uint32_t b) {
  uint32_t d;
  asm("mul.rn.bf16x2 %0, %1, %2;" : "=r"(d) : "r"(a), "r"(b));
  return d;
}
__device__ __forceinline__ uint32_t badd(uint32_t a, uint32_t b) {
  uint32_t d;
  asm("add.rn.bf16x2 %0, %1, %2;" : "=r"(d) : "r"(a), "r"(b));
  return d;
}
__device__ __forceinline__ float bf_lo(uint32_t x) { return __uint_as_float(x << 16); }
__device__ __forceinline__ float bf_hi(uint32_t x) { return __uint_as_float(x & 0xFFFF0000u); }
__device__ __forceinline__ float ex2(float x) {
  float y;
  asm("ex2.approx.ftz.f32 %0, %1;" : "=f"(y) : "f"(x));
  return y;
}
__device__ __forceinline__ float rcp(float x) {
  float y;
  asm("rcp.approx.ftz.f32 %0, %1;" : "=f"(y) : "f"(x));
  return y;
}
__device__ __forceinline__ void mma16816(float* d, uint32_t a0, uint32_t a1, uint32_t a2, uint32_t a3, uint32_t b0, uint32_t b1) {
  asm volatile("mma.sync.aligned.m16n8k16.row.col.f32.bf16.bf16.f32 {%0, %1, %2, %3}, {%4, %5, %6, %7}, {%8, %9}, {%0, %1, %2, %3};"
               : "+f"(d[0]), "+f"(d[1]), "+f"(d[2]), "+f"(d[3])
               : "r"(a0), "r"(a1), "r"(a2), "r"(a3), "r"(b0), "r"(b1));
}
__device__ __forceinline__ void mma1688(float* d, uint32_t a0, uint32_t a1, uint32_t b0) {
  asm volatile("mma.sync.aligned.m16n8k8.row.col.f32.bf16.bf16.f32 {%0, %1, %2, %3}, {%4, %5}, {%6}, {%0, %1, %2, %3};"
               : "+f"(d[0]), "+f"(d[1]), "+f"(d[2]), "+f"(d[3])
               : "r"(a0), "r"(a1), "r"(b0));
}

template <int N> struct WgRS;
template <int N> struct WgSST;
template <> struct WgRS<32> {
  template <uint32_t HB>
  static __device__ __forceinline__ void mma(float* d, const uint32_t* a, uint32_t db) {
    asm volatile("{\n.reg .pred p;\n.reg .b64 db;\nsetp.ne.b32 p, %22, 0;\n"
      "mov.b64 db, {%20, %21};\n"
      "wgmma.mma_async.sync.aligned.m64n32k16.f32.bf16.bf16 {"
      "%0, %1, %2, %3, %4, %5, %6, %7, %8, %9, %10, %11, %12, %13, %14, %15"
      "}, {%16, %17, %18, %19}, db, p, 1, 1, 1;\n}\n"
      : "+f"(d[0]), "+f"(d[1]), "+f"(d[2]), "+f"(d[3]), "+f"(d[4]), "+f"(d[5]), "+f"(d[6]), "+f"(d[7]),
        "+f"(d[8]), "+f"(d[9]), "+f"(d[10]), "+f"(d[11]), "+f"(d[12]), "+f"(d[13]), "+f"(d[14]), "+f"(d[15])
      : "r"(a[0]), "r"(a[1]), "r"(a[2]), "r"(a[3]), "r"(db), "n"(HB), "n"(1));
  }
  template <uint32_t HB>
  static __device__ __forceinline__ void set(float* d, const uint32_t* a, uint32_t db) {
    asm volatile("{\n.reg .pred p;\n.reg .b64 db;\nsetp.ne.b32 p, %22, 0;\n"
      "mov.b64 db, {%20, %21};\n"
      "wgmma.mma_async.sync.aligned.m64n32k16.f32.bf16.bf16 {"
      "%0, %1, %2, %3, %4, %5, %6, %7, %8, %9, %10, %11, %12, %13, %14, %15"
      "}, {%16, %17, %18, %19}, db, p, 1, 1, 1;\n}\n"
      : "=f"(d[0]), "=f"(d[1]), "=f"(d[2]), "=f"(d[3]), "=f"(d[4]), "=f"(d[5]), "=f"(d[6]), "=f"(d[7]),
        "=f"(d[8]), "=f"(d[9]), "=f"(d[10]), "=f"(d[11]), "=f"(d[12]), "=f"(d[13]), "=f"(d[14]), "=f"(d[15])
      : "r"(a[0]), "r"(a[1]), "r"(a[2]), "r"(a[3]), "r"(db), "n"(HB), "n"(0));
  }
};
template <> struct WgRS<64> {
  template <uint32_t HB>
  static __device__ __forceinline__ void mma(float* d, const uint32_t* a, uint32_t db) {
    asm volatile("{\n.reg .pred p;\n.reg .b64 db;\nsetp.ne.b32 p, %38, 0;\n"
      "mov.b64 db, {%36, %37};\n"
      "wgmma.mma_async.sync.aligned.m64n64k16.f32.bf16.bf16 {"
      "%0, %1, %2, %3, %4, %5, %6, %7, %8, %9, %10, %11, %12, %13, %14, %15, "
      "%16, %17, %18, %19, %20, %21, %22, %23, %24, %25, %26, %27, %28, %29, %30, %31"
      "}, {%32, %33, %34, %35}, db, p, 1, 1, 1;\n}\n"
      : "+f"(d[0]), "+f"(d[1]), "+f"(d[2]), "+f"(d[3]), "+f"(d[4]), "+f"(d[5]), "+f"(d[6]), "+f"(d[7]),
        "+f"(d[8]), "+f"(d[9]), "+f"(d[10]), "+f"(d[11]), "+f"(d[12]), "+f"(d[13]), "+f"(d[14]), "+f"(d[15]),
        "+f"(d[16]), "+f"(d[17]), "+f"(d[18]), "+f"(d[19]), "+f"(d[20]), "+f"(d[21]), "+f"(d[22]), "+f"(d[23]),
        "+f"(d[24]), "+f"(d[25]), "+f"(d[26]), "+f"(d[27]), "+f"(d[28]), "+f"(d[29]), "+f"(d[30]), "+f"(d[31])
      : "r"(a[0]), "r"(a[1]), "r"(a[2]), "r"(a[3]), "r"(db), "n"(HB), "n"(1));
  }
  template <uint32_t HB>
  static __device__ __forceinline__ void set(float* d, const uint32_t* a, uint32_t db) {
    asm volatile("{\n.reg .pred p;\n.reg .b64 db;\nsetp.ne.b32 p, %38, 0;\n"
      "mov.b64 db, {%36, %37};\n"
      "wgmma.mma_async.sync.aligned.m64n64k16.f32.bf16.bf16 {"
      "%0, %1, %2, %3, %4, %5, %6, %7, %8, %9, %10, %11, %12, %13, %14, %15, "
      "%16, %17, %18, %19, %20, %21, %22, %23, %24, %25, %26, %27, %28, %29, %30, %31"
      "}, {%32, %33, %34, %35}, db, p, 1, 1, 1;\n}\n"
      : "=f"(d[0]), "=f"(d[1]), "=f"(d[2]), "=f"(d[3]), "=f"(d[4]), "=f"(d[5]), "=f"(d[6]), "=f"(d[7]),
        "=f"(d[8]), "=f"(d[9]), "=f"(d[10]), "=f"(d[11]), "=f"(d[12]), "=f"(d[13]), "=f"(d[14]), "=f"(d[15]),
        "=f"(d[16]), "=f"(d[17]), "=f"(d[18]), "=f"(d[19]), "=f"(d[20]), "=f"(d[21]), "=f"(d[22]), "=f"(d[23]),
        "=f"(d[24]), "=f"(d[25]), "=f"(d[26]), "=f"(d[27]), "=f"(d[28]), "=f"(d[29]), "=f"(d[30]), "=f"(d[31])
      : "r"(a[0]), "r"(a[1]), "r"(a[2]), "r"(a[3]), "r"(db), "n"(HB), "n"(0));
  }
};
template <> struct WgSST<48> {
  template <uint32_t HA, uint32_t HB>
  static __device__ __forceinline__ void mma(float* d, uint32_t da, uint32_t db, int sc) {
    asm volatile("{\n.reg .pred p;\n.reg .b64 da, db;\nsetp.ne.b32 p, %28, 0;\n"
      "mov.b64 da, {%24, %25};\nmov.b64 db, {%26, %27};\n"
      "wgmma.mma_async.sync.aligned.m64n48k16.f32.bf16.bf16 {"
      "%0, %1, %2, %3, %4, %5, %6, %7, %8, %9, %10, %11, %12, %13, %14, %15, "
      "%16, %17, %18, %19, %20, %21, %22, %23"
      "}, da, db, p, 1, 1, 0, 1;\n}\n"
      : "+f"(d[0]), "+f"(d[1]), "+f"(d[2]), "+f"(d[3]), "+f"(d[4]), "+f"(d[5]), "+f"(d[6]), "+f"(d[7]),
        "+f"(d[8]), "+f"(d[9]), "+f"(d[10]), "+f"(d[11]), "+f"(d[12]), "+f"(d[13]), "+f"(d[14]), "+f"(d[15]),
        "+f"(d[16]), "+f"(d[17]), "+f"(d[18]), "+f"(d[19]), "+f"(d[20]), "+f"(d[21]), "+f"(d[22]), "+f"(d[23])
      : "r"(da), "n"(HA), "r"(db), "n"(HB), "r"(sc));
  }
};
template <> struct WgSST<80> {
  template <uint32_t HA, uint32_t HB>
  static __device__ __forceinline__ void mma(float* d, uint32_t da, uint32_t db, int sc) {
    asm volatile("{\n.reg .pred p;\n.reg .b64 da, db;\nsetp.ne.b32 p, %44, 0;\n"
      "mov.b64 da, {%40, %41};\nmov.b64 db, {%42, %43};\n"
      "wgmma.mma_async.sync.aligned.m64n80k16.f32.bf16.bf16 {"
      "%0, %1, %2, %3, %4, %5, %6, %7, %8, %9, %10, %11, %12, %13, %14, %15, "
      "%16, %17, %18, %19, %20, %21, %22, %23, %24, %25, %26, %27, %28, %29, %30, %31, "
      "%32, %33, %34, %35, %36, %37, %38, %39"
      "}, da, db, p, 1, 1, 0, 1;\n}\n"
      : "+f"(d[0]), "+f"(d[1]), "+f"(d[2]), "+f"(d[3]), "+f"(d[4]), "+f"(d[5]), "+f"(d[6]), "+f"(d[7]),
        "+f"(d[8]), "+f"(d[9]), "+f"(d[10]), "+f"(d[11]), "+f"(d[12]), "+f"(d[13]), "+f"(d[14]), "+f"(d[15]),
        "+f"(d[16]), "+f"(d[17]), "+f"(d[18]), "+f"(d[19]), "+f"(d[20]), "+f"(d[21]), "+f"(d[22]), "+f"(d[23]),
        "+f"(d[24]), "+f"(d[25]), "+f"(d[26]), "+f"(d[27]), "+f"(d[28]), "+f"(d[29]), "+f"(d[30]), "+f"(d[31]),
        "+f"(d[32]), "+f"(d[33]), "+f"(d[34]), "+f"(d[35]), "+f"(d[36]), "+f"(d[37]), "+f"(d[38]), "+f"(d[39])
      : "r"(da), "n"(HA), "r"(db), "n"(HB), "r"(sc));
  }
};
template <> struct WgSST<192> {
  template <uint32_t HA, uint32_t HB>
  static __device__ __forceinline__ void mma(float* d, uint32_t da, uint32_t db, int sc) {
    asm volatile("{\n.reg .pred p;\n.reg .b64 da, db;\nsetp.ne.b32 p, %100, 0;\n"
      "mov.b64 da, {%96, %97};\nmov.b64 db, {%98, %99};\n"
      "wgmma.mma_async.sync.aligned.m64n192k16.f32.bf16.bf16 {"
      "%0, %1, %2, %3, %4, %5, %6, %7, %8, %9, %10, %11, %12, %13, %14, %15, "
      "%16, %17, %18, %19, %20, %21, %22, %23, %24, %25, %26, %27, %28, %29, %30, %31, "
      "%32, %33, %34, %35, %36, %37, %38, %39, %40, %41, %42, %43, %44, %45, %46, %47, "
      "%48, %49, %50, %51, %52, %53, %54, %55, %56, %57, %58, %59, %60, %61, %62, %63, "
      "%64, %65, %66, %67, %68, %69, %70, %71, %72, %73, %74, %75, %76, %77, %78, %79, "
      "%80, %81, %82, %83, %84, %85, %86, %87, %88, %89, %90, %91, %92, %93, %94, %95"
      "}, da, db, p, 1, 1, 0, 1;\n}\n"
      : "+f"(d[0]), "+f"(d[1]), "+f"(d[2]), "+f"(d[3]), "+f"(d[4]), "+f"(d[5]), "+f"(d[6]), "+f"(d[7]),
        "+f"(d[8]), "+f"(d[9]), "+f"(d[10]), "+f"(d[11]), "+f"(d[12]), "+f"(d[13]), "+f"(d[14]), "+f"(d[15]),
        "+f"(d[16]), "+f"(d[17]), "+f"(d[18]), "+f"(d[19]), "+f"(d[20]), "+f"(d[21]), "+f"(d[22]), "+f"(d[23]),
        "+f"(d[24]), "+f"(d[25]), "+f"(d[26]), "+f"(d[27]), "+f"(d[28]), "+f"(d[29]), "+f"(d[30]), "+f"(d[31]),
        "+f"(d[32]), "+f"(d[33]), "+f"(d[34]), "+f"(d[35]), "+f"(d[36]), "+f"(d[37]), "+f"(d[38]), "+f"(d[39]),
        "+f"(d[40]), "+f"(d[41]), "+f"(d[42]), "+f"(d[43]), "+f"(d[44]), "+f"(d[45]), "+f"(d[46]), "+f"(d[47]),
        "+f"(d[48]), "+f"(d[49]), "+f"(d[50]), "+f"(d[51]), "+f"(d[52]), "+f"(d[53]), "+f"(d[54]), "+f"(d[55]),
        "+f"(d[56]), "+f"(d[57]), "+f"(d[58]), "+f"(d[59]), "+f"(d[60]), "+f"(d[61]), "+f"(d[62]), "+f"(d[63]),
        "+f"(d[64]), "+f"(d[65]), "+f"(d[66]), "+f"(d[67]), "+f"(d[68]), "+f"(d[69]), "+f"(d[70]), "+f"(d[71]),
        "+f"(d[72]), "+f"(d[73]), "+f"(d[74]), "+f"(d[75]), "+f"(d[76]), "+f"(d[77]), "+f"(d[78]), "+f"(d[79]),
        "+f"(d[80]), "+f"(d[81]), "+f"(d[82]), "+f"(d[83]), "+f"(d[84]), "+f"(d[85]), "+f"(d[86]), "+f"(d[87]),
        "+f"(d[88]), "+f"(d[89]), "+f"(d[90]), "+f"(d[91]), "+f"(d[92]), "+f"(d[93]), "+f"(d[94]), "+f"(d[95])
      : "r"(da), "n"(HA), "r"(db), "n"(HB), "r"(sc));
  }
};

struct FftConst {
  uint32_t f[2][4], fi[4][4];
  float ta[4], tb[4];
};
__device__ __forceinline__ void cis(int m, float scale, float& c, float& s) {
  const float a = (float)m * (-6.283185307179586f * scale);
  c = __cosf(a);
  s = __sinf(a);
}
__device__ __forceinline__ void fft_tables(uint32_t (&v)[12], int tw) {
  const int row = tw >> 2, ch = tw & 3;
#pragma unroll
  for (int i = 0; i < 4; i++) {
    float c[2], s[2], x[2];
#pragma unroll
    for (int e = 0; e < 2; e++) {
      cis((((32 * (8 * ch + 2 * i + e) + 15) * (4 * row - 63) + 2048) & 4095) - 2048, 1.f / 4096, c[e], s[e]);
      float gc, gs;
      cis((((row & 15) * (8 * (ch & 1) + 2 * i + e) + 8) & 15) - 8, 1.f / 16, gc, gs);
      x[e] = (row >> 4) == (ch >> 1) ? gc : (ch >> 1) ? gs : -gs;
    }
    v[i] = pack2(c[0] * 0.125f, c[1] * 0.125f);
    v[4 + i] = pack2(s[0] * 0.125f, s[1] * 0.125f);
    v[8 + i] = pack2(x[0], x[1]);
  }
#pragma unroll
  for (int i = 0; i < 12; i++) asm volatile("" : "+r"(v[i]));
}
__device__ __forceinline__ void fft_tables_store(const uint32_t (&v)[12], uint32_t sb, int tw) {
  const int row = tw >> 2;
  const uint32_t x = ((tw ^ (row >> 1)) & 3) << 4, a = sb + OFF_FT + (16 * (row >> 3) + (row & 7)) * 64 + x;
  sts128(a, v[0], v[1], v[2], v[3]);
  sts128(a + 512, v[4], v[5], v[6], v[7]);
  sts128(sb + OFF_GT + row * 64 + x, v[8], v[9], v[10], v[11]);
}
__device__ __forceinline__ void fft_twiddles(float (&v)[4], int tw) {
#pragma unroll
  for (int i = 0; i < 2; i++) {
    float c, s;
    cis((2 * (2 * (tw & 3) + i) - 15) * (4 * (tw >> 2) - 63), 1.f / 4096, c, s);
    v[2 * i] = __fdividef(-s, 1.f + c);
    v[2 * i + 1] = s;
  }
  pin<4>(v);
}
__device__ __forceinline__ void fft_matrices(FftConst& k, uint32_t sb, int w, int lane) {
  const uint32_t x = (lane >> 1) & 3;
  const uint4 t0 = lds128(sb + OFF_TT + 512 * w + 16 * lane), t1 = lds128(sb + OFF_TT + 512 * w + 16 * (lane ^ 3));
  k.ta[0] = __uint_as_float(t0.x); k.tb[0] = __uint_as_float(t0.y); k.ta[1] = __uint_as_float(t0.z); k.tb[1] = __uint_as_float(t0.w);
  k.ta[3] = __uint_as_float(t1.x); k.tb[3] = __uint_as_float(t1.y); k.ta[2] = __uint_as_float(t1.z); k.tb[2] = __uint_as_float(t1.w);
#pragma unroll
  for (int i = 0; i < 2; i++) {
    ldsm4(k.f[i], sb + OFF_FT + (16 * w + (lane & 15)) * 64 + (((2 * i + (lane >> 4)) ^ x) << 4));
    ldsm4t(k.fi[i], sb + OFF_FT + (32 * i + lane) * 64 + ((w ^ x) << 4));
#pragma unroll
    for (int j = 0; j < 4; j++) {
      k.fi[2 + i][j] = (j & 1) ? k.fi[i][j - 1] ^ 0x80008000u : k.fi[i][j + 1];
      asm volatile("" : "+r"(k.fi[2 + i][j]));
    }
  }
}
__device__ __forceinline__ void rot(bool inv, float& x, float& y, float a, float b) {
  x = fmaf(inv ? -a : a, y, x);
  y = fmaf(inv ? -b : b, x, y);
  x = fmaf(inv ? -a : a, y, x);
}
__device__ __forceinline__ void twiddle_fwd(uint32_t (&a)[4][4], float* d, const FftConst& k) {
#pragma unroll
  for (int q = 0; q < 4; q++)
#pragma unroll
    for (int j = 0; j < 2; j++) {
      float* x = d + 8 * q + 4 * j;
      rot(j, x[0], x[2], k.ta[2 * j], k.tb[2 * j]);
      rot(j, x[1], x[3], k.ta[2 * j + 1], k.tb[2 * j + 1]);
      a[q & 2][2 * j + (q & 1)] = pack2(x[0], x[1]);
      a[(q & 2) + 1][2 * j + (q & 1)] = pack2(x[2], x[3]);
    }
}
__device__ __forceinline__ void g_step(float* d, const uint32_t (&a)[4][4], uint32_t dre, uint32_t dim) {
  WgRS<32>::set<HI_SW64>(d, a[0], dre);
  WgRS<32>::set<HI_SW64>(d + 16, a[2], dre);
  WgRS<32>::mma<HI_SW64>(d, a[1], dim);
  WgRS<32>::mma<HI_SW64>(d + 16, a[3], dim);
  wg_commit();
}

__device__ __forceinline__ void conv_channel(const FftConst& k, uint32_t sb, int c, int wg, int w, int lane) {
  const uint32_t cb = sb + off_ch(c), bars = sb + OFF_BAR;
  const uint32_t du = desc_lo(cb, 1024), dg = desc_lo(sb + OFF_GT, 16), dz = desc_lo(cb + U_BYTES, 16);
  float U[32], H[32];
  uint32_t a[4][4], e[4][4];
  const float dv = __uint_as_float(lds32(sb + OFF_D + 4 * c));
  wg_fence();
  WgRS<64>::set<HI_SW32>(H, k.f[0], du + 256);
  WgRS<64>::mma<HI_SW32>(H, k.f[1], du + 256 + 32);
  wg_commit();
  wg_wait<0>();
  pin<32>(H);
  TSM(w == 0 && c == 1, 114);
  twiddle_fwd(a, H, k);
  asm volatile("" : "+r"(a[0][0]), "+r"(a[1][1]), "+r"(a[2][2]), "+r"(a[3][3]));
  TSM(w == 0 && c == 1, 127);
  if (ATT_GATE && H_EARLY) mbar_wait(bars + 8 * B_ATTN, 0);
  mbar_wait(bars + 8 * (B_U + (c < 3 ? c : 3)), 0);
  TSM(w == 0 && c < 3, 7 + wg);
  wg_fence();
  WgRS<64>::set<HI_SW32>(U, k.f[0], du);
  WgRS<64>::mma<HI_SW32>(U, k.f[1], du + 32);
  wg_commit();
  g_step(H, a, dg, dg + 64);
  wg_wait<1>();
  pin<32>(U);
  twiddle_fwd(e, U, k);
  wg_fence();
  g_step(U, e, dg, dg + 64);
  wg_wait<0>();
  pin<32>(U);
  pin<32>(H);
#pragma unroll
  for (int j = 0; j < 2; j++) {
    float pr[4][2], pi[4][2];
#pragma unroll
    for (int x = 0; x < 2; x++) {
      H[4 * j + x] += dv;
#pragma unroll
      for (int m = 0; m < 4; m++) {
#pragma unroll
        for (int q = 0; q <= m; q++) {
          const int ih = 16 * (q >> 1) + 2 * (q & 1) + 4 * j + x, iu = 16 * ((m - q) >> 1) + 2 * ((m - q) & 1) + 4 * j + x;
          pr[m][x] = q ? fmaf(H[ih], U[iu], pr[m][x]) : H[ih] * U[iu];
          pi[m][x] = q ? fmaf(H[ih], U[iu + 8], pi[m][x]) : H[ih] * U[iu + 8];
          pr[m][x] = fmaf(-H[ih + 8], U[iu + 8], pr[m][x]);
          pi[m][x] = fmaf(H[ih + 8], U[iu], pi[m][x]);
        }
      }
    }
#pragma unroll
    for (int m = 0; m < 4; m++) {
      a[m & 2][2 * j + (m & 1)] = pack2(pr[m][0], pr[m][1]);
      a[(m & 2) + 1][2 * j + (m & 1)] = pack2(pi[m][0], pi[m][1]);
    }
  }
  wg_fence();
  g_step(U, a, dg + 64, dg);
  const uint32_t za = cb + U_BYTES + (8 * w + (lane & 7)) * 128 + (((lane >> 3) ^ (lane & 7)) << 4);
  const uint32_t ya = cb + (lane >> 4) * 1024 + (8 * w + (lane & 7)) * 32 + ((((lane >> 3) ^ (lane >> 2)) & 1) << 4);
  wg_sync(1 + wg);
  wg_wait<0>();
  pin<32>(U);
  TSIF(w == 0, 80 + c);
#pragma unroll
  for (int p = 0; p < 2; p++) {
#pragma unroll
    for (int i = 0; i < 4; i++) {
      const int j = i & 1;
      float* x = U + 16 * p + 4 * j + (i & 2);
      rot(!j, x[8], x[0], k.ta[2 * j], k.tb[2 * j]);
      rot(!j, x[9], x[1], k.ta[2 * j + 1], k.tb[2 * j + 1]);
      e[p][i] = pack2(x[8], x[9]);
      e[2 + p][i] = pack2(x[0], x[1]);
    }
    stsm4(za ^ (64 * p), e[p]);
    stsm4((za ^ (64 * p)) + 4096, e[2 + p]);
  }
  fence_async_smem();
  wg_sync(1 + wg);
  wg_fence();
  WgRS<64>::set<HI_SW128>(H, k.fi[0], dz);
#pragma unroll
  for (int ks = 1; ks < 4; ks++) WgRS<64>::mma<HI_SW128>(H, k.fi[ks], dz + 128 * ks);
  wg_commit();
  wg_wait<0>();
  pin<32>(H);
  TSIF(w == 0, 88 + c);
#pragma unroll
  for (int j = 0; j < 8; j++)
    a[j >> 2][j & 3] = j < 2 ? pack2(H[4 * j], H[4 * j + 1]) : pack2(H[4 * j] + H[4 * j - 6], H[4 * j + 1] + H[4 * j - 5]);
  stsm4(ya, a[0]);
  stsm4(ya + 2048, a[1]);
  fence_async_smem();
  __syncwarp();
}

__device__ __forceinline__ void prep_slab(uint4* res, const uint2* sw, uint32_t sb, int slab, int w, int lane) {
  const int t = lane & 3, tp = (lane & 7) >> 1, pos = 8 * tp + 2 * (((lane >> 3) + tp) & 3) + (lane & 1);
  const uint32_t base = sb + OFF_KVS + slab * KVS_BYTES + pos * 128;
  uint32_t kk[2][4][4], vv[2][4];
  mbar_wait(sb + OFF_BAR + 8 * (B_KV + slab), 0);
#pragma unroll
  for (int h = 0; h < 2; h++) {
#pragma unroll
    for (int j = 0; j < 4; j++) {
      const uint32_t a = base + 128 * j;
      ldsm4t(kk[h][j], a + (((w + 4 * h) ^ ((a >> 7) & 7)) << 4));
    }
    const uint32_t a = base + KVS_V;
    ldsm4t(vv[h], a + (((w + 4 * h) ^ ((a >> 7) & 7)) << 4));
  }
#pragma unroll
  for (int h = 0; h < 2; h++) {
    uint32_t (&k)[4][4] = kk[h];
    uint32_t (&v)[4] = vv[h];
    const uint32_t w0 = __byte_perm(sw[h].x, 0, 0x1010), w1 = __byte_perm(sw[h].x, 0, 0x3232);
    const uint32_t w2 = __byte_perm(sw[h].y, 0, 0x1010), w3 = __byte_perm(sw[h].y, 0, 0x3232);
#pragma unroll
    for (int m = 0; m < 4; m++)
      v[m] = bmul(badd(badd(badd(bmul(k[0][m], w3), bmul(k[1][m], w2)), bmul(k[2][m], w1)), bmul(k[3][m], w0)), v[m]);
    uint32_t a[4];
#pragma unroll
    for (int m = 0; m < 4; m++) a[m] = (t & 1) ? v[(m + 3) & 3] : v[m];
    res[h] = (t & 2) ? make_uint4(a[2], a[3], a[0], a[1]) : make_uint4(a[0], a[1], a[2], a[3]);
  }
}

__device__ __forceinline__ void prep_gate(const Params& p, int b, int w, int lane) {
  uint2 gw[5], x[4][5];
#pragma unroll
  for (int j = 0; j < 5; j++) gw[j] = ldg64(reinterpret_cast<const uint2*>(p.gate_w) + lane + 32 * j);
#pragma unroll
  for (int i = 0; i < 4; i++)
#pragma unroll
    for (int j = 0; j < 5; j++)
      x[i][j] = ldg64(reinterpret_cast<const uint2*>(p.q) + (16 * b + 4 * w + i) * (DIM / 4) + lane + 32 * j);
  float s[4];
#pragma unroll
  for (int i = 0; i < 4; i++) {
    s[i] = 0.f;
#pragma unroll
    for (int j = 0; j < 5; j++) {
      const uint32_t m0 = bmul(x[i][j].x, gw[j].x), m1 = bmul(x[i][j].y, gw[j].y);
      s[i] += (bf_lo(m0) + bf_hi(m0)) + (bf_lo(m1) + bf_hi(m1));
    }
  }
  const bool h = lane & 16, q = lane & 8;
  const float a = (h ? s[2] : s[0]) + __shfl_xor_sync(0xffffffffu, h ? s[0] : s[2], 16);
  const float c = (h ? s[3] : s[1]) + __shfl_xor_sync(0xffffffffu, h ? s[1] : s[3], 16);
  float z = (q ? c : a) + __shfl_xor_sync(0xffffffffu, q ? a : c, 8);
#pragma unroll
  for (int o = 4; o > 0; o >>= 1) z += __shfl_xor_sync(0xffffffffu, z, o);
  z = bf_lo(pack2(z, 0.f));
  if ((lane & 7) == 0) g_gate[16 * b + 4 * w + (lane >> 3)] = bf_lo(pack2(__fdividef(1.f, 1.f + __expf(-z)), 0.f));
}

__device__ __forceinline__ uint32_t bmax(uint32_t a, uint32_t b) {
  uint32_t d;
  asm("max.bf16x2 %0, %1, %2;" : "=r"(d) : "r"(a), "r"(b));
  return d;
}
__device__ __forceinline__ void softmax_two(const float (&l)[2][2], uint32_t& p0, uint32_t& p1) {
  constexpr float kScale = 0.22360679774997896f, kLog2e = 1.4426950408889634f;
  const uint32_t r0 = pack2(l[0][0], l[1][0]), r1 = pack2(l[0][1], l[1][1]);
  const uint32_t x0 = pack2(bf_lo(r0) * kScale, bf_hi(r0) * kScale), x1 = pack2(bf_lo(r1) * kScale, bf_hi(r1) * kScale);
  uint32_t m = bmax(x0, x1);
  m = bmax(m, __shfl_xor_sync(0xffffffffu, m, 1));
  m = bmax(m, __shfl_xor_sync(0xffffffffu, m, 2));
  const float m0 = bf_lo(m) * kLog2e, m1 = bf_hi(m) * kLog2e;
  p0 = pack2(ex2(bf_lo(x0) * kLog2e - m0), ex2(bf_lo(x1) * kLog2e - m0));
  p1 = pack2(ex2(bf_hi(x0) * kLog2e - m1), ex2(bf_hi(x1) * kLog2e - m1));
}

__device__ __forceinline__ void halo_read(uint32_t (&kpv)[10], uint32_t (&vpv)[10], uint32_t (&tg)[7], const uint4* hp) {
#pragma unroll
  for (int j = 0; j < 7; j++) {
    uint32_t x0, x1, x2;
    asm volatile("ld.relaxed.gpu.global.v4.u32 {%0, %1, %2, %3}, [%4];"
                 : "=r"(x0), "=r"(x1), "=r"(x2), "=r"(tg[j]) : "l"(hp + 32 * j) : "memory");
    if (j < 4) kpv[3 * j] = x0; else vpv[3 * j - 10] = x0;
    if (j < 3) kpv[3 * j + 1] = x1; else vpv[3 * j - 9] = x1;
    if (j < 3) kpv[3 * j + 2] = x2; else if (j < 6) vpv[3 * j - 8] = x2;
  }
}

template <int ROT>
__device__ __forceinline__ void pack_qkv(const float* acc, uint32_t (&qlo)[10], uint32_t (&qhi)[10], uint32_t (&klo)[10],
                                         uint32_t (&khi)[10], uint32_t (&vlo)[10], uint32_t (&vhi)[10]) {
#pragma unroll
  for (int j = 0; j < 10; j++) {
    const int x = (j + ROT) % 10, tq = x < 8 ? x : 16 + x, tk = x < 8 ? 8 + x : 18 + x, tv = x < 8 ? 16 + x : 20 + x;
    khi[j] = pack2(acc[4 * tk + 2], acc[4 * tk + 3]);
    vhi[j] = movm(pack2(acc[4 * tv + 2], acc[4 * tv + 3]));
    qlo[j] = pack2(acc[4 * tq], acc[4 * tq + 1]);
    qhi[j] = pack2(acc[4 * tq + 2], acc[4 * tq + 3]);
    klo[j] = pack2(acc[4 * tk], acc[4 * tk + 1]);
    vlo[j] = pack2(acc[4 * tv], acc[4 * tv + 1]);
    asm volatile("" : "+r"(khi[j]), "+r"(qlo[j]), "+r"(qhi[j]), "+r"(klo[j]), "+r"(vlo[j]));
  }
}

template <int ROT> __device__ __forceinline__ void halo_send(const float* acc, uint4* ho, uint32_t tag) {
#pragma unroll
  for (int j = 0; j < 7; j++) {
    uint32_t x[3];
#pragma unroll
    for (int e = 0; e < 3; e++) {
      const int i = 3 * j + e, y = (i % 10 + ROT) % 10, tk = y < 8 ? 8 + y : 18 + y, tv = y < 8 ? 16 + y : 20 + y;
      x[e] = i < 10 ? pack2(acc[4 * tk + 2], acc[4 * tk + 3]) : i < 20 ? movm(pack2(acc[4 * tv + 2], acc[4 * tv + 3])) : 0u;
    }
    asm volatile("st.relaxed.gpu.global.v4.u32 [%0], {%1, %2, %3, %4};" ::"l"(ho + 32 * j), "r"(x[0]), "r"(x[1]), "r"(x[2]), "r"(tag) : "memory");
  }
}

__device__ __forceinline__ void attention(float* acc, uint32_t sb, int b, int par, int w, int lane, uint32_t tag) {
  const int g = lane >> 2, t = lane & 3;
  uint32_t klo[10], khi[10], vlo[10], vhi[10], qlo[10], qhi[10], kpv[10], vpv[10];
  if (HALO_FIRST && w == 3 && b < NCTA - 8) {
    uint4* ho = g_halo + (b * 2 + par) * 224 + lane;
    if (tail_first(b & 7)) halo_send<8>(acc, ho, tag);
    else halo_send<0>(acc, ho, tag);
    TSIF(par == 0, 76);
    pin<120>(acc);
  }
  if (tail_first(b & 7)) pack_qkv<8>(acc, qlo, qhi, klo, khi, vlo, vhi);
  else pack_qkv<0>(acc, qlo, qhi, klo, khi, vlo, vhi);
  const uint32_t xa = sb + OFF_KVX + (par * 3) * 2560 + lane * 16;
  if (w < 3) {
    sts128(xa + w * 2560, khi[0], khi[1], khi[2], khi[3]);
    sts128(xa + w * 2560 + 512, khi[4], khi[5], khi[6], khi[7]);
    sts128(xa + w * 2560 + 1024, khi[8], khi[9], vhi[0], vhi[1]);
    sts128(xa + w * 2560 + 1536, vhi[2], vhi[3], vhi[4], vhi[5]);
    sts128(xa + w * 2560 + 2048, vhi[6], vhi[7], vhi[8], vhi[9]);
  } else if (!HALO_FIRST && b < NCTA - 8) {
    uint4* ho = g_halo + (b * 2 + par) * 224 + lane;
#pragma unroll
    for (int j = 0; j < 7; j++) {
      const uint32_t x0 = j < 4 ? khi[3 * j] : vhi[3 * j - 10], x1 = j < 3 ? khi[3 * j + 1] : vhi[3 * j - 9];
      const uint32_t x2 = j < 3 ? khi[3 * j + 2] : j < 6 ? vhi[3 * j - 8] : 0u;
      asm volatile("st.relaxed.gpu.global.v4.u32 [%0], {%1, %2, %3, %4};" ::"l"(ho + 32 * j), "r"(x0), "r"(x1), "r"(x2), "r"(tag) : "memory");
    }
  }
  TSIF(par == 0 && w == 1, 64);
  TSIF(par == 0 && w == 3 && !HALO_FIRST, 76);
#pragma unroll
  for (int j = 0; j < 10; j++) vlo[j] = movm(vlo[j]);
  const bool far0 = 2 * t > g, far1 = 2 * t + 1 > g;
  const uint32_t mfar = (far0 ? 0x0000FFFFu : 0u) | (far1 ? 0xFFFF0000u : 0u);
  float slo[4][2], shi[4][2], lg[2][2];
  uint32_t phi[4], plo[4], qml[4], qmh[4];
#pragma unroll
  for (int h = 0; h < 4; h++) {
    const int f = h == 0 ? 0 : h == 1 ? 3 : h == 2 ? 5 : 8, hf = h < 2 ? 2 : 7;
    const bool mine = (h & 1) ? t >= 2 : t < 2;
    qml[h] = mine ? qlo[hf] : 0u;
    qmh[h] = mine ? qhi[hf] : 0u;
    float a[4] = {0.f, 0.f, 0.f, 0.f}, c[4] = {0.f, 0.f, 0.f, 0.f};
    mma16816(a, qlo[f], qhi[f], qlo[f + 1], qhi[f + 1], klo[f], klo[f + 1]);
    mma16816(c, qlo[f], qhi[f], qlo[f + 1], qhi[f + 1], khi[f], khi[f + 1]);
    mma1688(a, qml[h], qmh[h], klo[hf]);
    mma1688(c, qml[h], qmh[h], khi[hf]);
    slo[h][0] = a[0];
    slo[h][1] = a[1];
    shi[h][0] = lg[h & 1][0] = far0 ? a[2] : c[2];
    shi[h][1] = lg[h & 1][1] = far1 ? a[3] : c[3];
    if (!ATT_MERGE && (h & 1)) softmax_two(lg, phi[h - 1], phi[h]);
  }
  TSIF(par == 0 && w == 1, 65);
  wg_sync(1 + par);
  TSIF(par == 0 && w == 1, 66);
  const bool nohist = (w == 0) && (b < 8);
  const uint4* hp = g_halo + ((b - 8) * 2 + par) * 224 + lane;
  uint32_t tg[7];
  if (w > 0) {
    const uint4 v0 = lds128(xa + (w - 1) * 2560), v1 = lds128(xa + (w - 1) * 2560 + 512), v2 = lds128(xa + (w - 1) * 2560 + 1024);
    const uint4 v3 = lds128(xa + (w - 1) * 2560 + 1536), v4 = lds128(xa + (w - 1) * 2560 + 2048);
    kpv[0] = v0.x; kpv[1] = v0.y; kpv[2] = v0.z; kpv[3] = v0.w; kpv[4] = v1.x; kpv[5] = v1.y; kpv[6] = v1.z; kpv[7] = v1.w;
    kpv[8] = v2.x; kpv[9] = v2.y; vpv[0] = v2.z; vpv[1] = v2.w; vpv[2] = v3.x; vpv[3] = v3.y; vpv[4] = v3.z; vpv[5] = v3.w;
    vpv[6] = v4.x; vpv[7] = v4.y; vpv[8] = v4.z; vpv[9] = v4.w;
  } else if (nohist) {
#pragma unroll
    for (int j = 0; j < 10; j++) kpv[j] = vpv[j] = 0u;
  } else {
    TSIF(par == 0, 77);
    halo_read(kpv, vpv, tg, hp);
  }
  if (w == 0 && !nohist) {
    int spins = 0;
    while (true) {
      bool ok = true;
#pragma unroll
      for (int j = 0; j < 7; j++) ok = ok && tg[j] == tag;
      if (__all_sync(0xffffffffu, ok) || ++spins > SPIN_LIMIT) break;
      halo_read(kpv, vpv, tg, hp);
    }
    TSIF(par == 0, 79);
  }
#pragma unroll
  for (int h = 0; h < 4; h++) {
    const int f = h == 0 ? 0 : h == 1 ? 3 : h == 2 ? 5 : 8, hf = h < 2 ? 2 : 7;
    float a[4] = {0.f, 0.f, 0.f, 0.f};
    mma16816(a, qlo[f], qhi[f], qlo[f + 1], qhi[f + 1], kpv[f], kpv[f + 1]);
    mma1688(a, qml[h], qmh[h], kpv[hf]);
    const float ninf = __int_as_float(0xff800000);
    lg[h & 1][0] = far0 ? (nohist ? ninf : a[0]) : slo[h][0];
    lg[h & 1][1] = far1 ? (nohist ? ninf : a[1]) : slo[h][1];
    if (h & 1) {
      softmax_two(lg, plo[h - 1], plo[h]);
      if (ATT_MERGE) {
        const float lh[2][2] = {{shi[h - 1][0], shi[h - 1][1]}, {shi[h][0], shi[h][1]}};
        softmax_two(lh, phi[h - 1], phi[h]);
      }
    }
  }
  TSIF(par == 0 && w <= 1, 67 + w);
  uint32_t ov[20];
#pragma unroll
  for (int hp = 0; hp < 2; hp++) {
    const int hf = hp ? 7 : 2;
    float sh[4] = {0.f, 0.f, 0.f, 0.f}, i0 = 0.f, i1 = 0.f;
#pragma unroll
    for (int e = 0; e < 2; e++) {
      const int h = 2 * hp + e, f = h == 0 ? 0 : h == 1 ? 3 : h == 2 ? 5 : 8;
      const uint32_t a0 = plo[h] & mfar, a2 = plo[h] & ~mfar, a3 = phi[h] & mfar, c1 = phi[h] & ~mfar;
      float sum[4] = {0.f, 0.f, 0.f, 0.f};
      mma1688(sum, plo[h], phi[h], 0x3F803F80u);
      const float r0 = rcp(sum[0]), r1 = rcp(sum[2]);
#pragma unroll
      for (int j = f; j < f + 2; j++) {
        float o[4] = {0.f, 0.f, 0.f, 0.f};
        mma16816(o, a0, 0u, a2, a3, vpv[j], vlo[j]);
        mma1688(o, 0u, c1, vhi[j]);
        ov[2 * j] = pack2(o[0] * r0, o[1] * r0);
        ov[2 * j + 1] = pack2(o[2] * r1, o[3] * r1);
      }
      const bool mine = e ? g >= 4 : g < 4;
      mma16816(sh, a0, 0u, a2, a3, mine ? vpv[hf] : 0u, mine ? vlo[hf] : 0u);
      mma1688(sh, 0u, c1, mine ? vhi[hf] : 0u);
      if (e == 0 || t >= 2) {
        i0 = r0;
        i1 = r1;
      }
    }
    ov[2 * hf] = pack2(sh[0] * i0, sh[1] * i0);
    ov[2 * hf + 1] = pack2(sh[2] * i1, sh[3] * i1);
  }
  TS(32 + 4 * par + w);
  mbar_wait(sb + OFF_BAR + 8 * B_P1, 0);
  const uint32_t oa = sb + OFF_OA + (lane >> 4) * 2048 + (32 * w + 2 * (lane & 15) + par) * 16;
#pragma unroll
  for (int j = 0; j < 5; j++) stsm4(oa + 4096 * j, ov + 4 * j);
  TSIF(par == 0 && w == 0, 120);
  fence_async_smem();
  TSIF(par == 0 && w == 0, 121);
  __syncwarp();
  if (lane == 0) mbar_arrive(sb + OFF_BAR + 8 * B_ATTN);
  TSM(w == 0 || w == 2, 122 + par + (w == 2 ? 3 : 0));
}

struct Maps {
  CUtensorMap x, wm, wt, k, v, y, wo, qm, qt, om, ot, u;
};

__device__ __forceinline__ void load_stage(uint32_t sb, int kb, int b, const Maps& m) {
  const uint32_t st = sb + (kb & 3) * STAGE_BYTES, bar = sb + OFF_BAR + 8 * (B_FULL1 + (kb & 3));
  const int r = b >> 3, hg = b & 7, slab = kb - KV_KB;
  const bool kv = slab >= 0 && slab < 5;
  const uint32_t kbar = sb + OFF_BAR + 8 * (B_KV + slab), dst = sb + OFF_KVS + slab * KVS_BYTES;
  mbar_expect_tx(bar, STAGE_BYTES);
  if (kv) mbar_expect_tx(kbar, KVS_BYTES);
  tma_3d(st, &m.x, 64 * kb, 64 * r, 0, bar);
  if (kv && KV_MIX) tma_3d(dst, &m.k, 0, 32 * (b >> 1) - 3, 2 * slab + (b & 1), kbar);
  tma_3d(st + ST_W, &m.wm, 80 * hg + (tail_first(hg) ? 16 : 0), 64 * kb, 0, bar);
  if (kv && KV_MIX) tma_3d(dst + KVS_V, &m.v, 0, 32 * (b >> 1), 2 * slab + (b & 1), kbar);
  tma_3d(st + ST_WT, &m.wt, 80 * hg + (tail_first(hg) ? 0 : 64), 64 * kb, 0, bar);
  if (kv && !KV_MIX) tma_3d(dst, &m.k, 0, 32 * (b >> 1) - 3, 2 * slab + (b & 1), kbar);
  if (kv && !KV_MIX) tma_3d(dst + KVS_V, &m.v, 0, 32 * (b >> 1), 2 * slab + (b & 1), kbar);
}

__global__ void __launch_bounds__(NTHR, 1) fused_kernel(const __grid_constant__ Maps m, const Params p) {
  extern __shared__ __align__(1024) uint8_t smem[];
  const uint32_t sb = (uint32_t)__cvta_generic_to_shared(smem);
  const uint32_t bars = sb + OFF_BAR;
  const int tid = threadIdx.x, lane = tid & 31;
  int b = blockIdx.x;
  if (BMAP == 1) b = (((b & 63) >> 3) * 2 + (b & 1)) * 8 + (((b < 64 ? 0x6521 : 0x7430) >> (4 * ((b >> 1) & 3))) & 7);
  if (BMAP == 2) b = ((b & 63) >> 2) * 8 + (((b < 64 ? 0x6521 : 0x7430) >> (4 * (b & 3))) & 7);
  if (BMAP == 3) b = (((b & 63) >> 3) * 2 + (b & 1)) * 8 + (((b < 64 ? 0x7430 : 0x6521) >> (4 * ((b >> 1) & 3))) & 7);
  if (BMAP == 4) b = (((b >> 4) * 2 + (b & 1)) * 8) + ((b >> 1) & 7);
  if (BMAP == 5) b = 127 - b;
  const int r = b >> 3, hg = b & 7;

  if (tid == T_ISSUE) {
    TSM(true, 0);
#pragma unroll
    for (int i = 0; i < 4; i++) mbar_init(bars + 8 * (B_FULL1 + i), 1);
#pragma unroll
    for (int i = 0; i < 3; i++) mbar_init(bars + 8 * (B_KV + i), 1);
    fence_async_smem();
#pragma unroll 1
    for (int kb = 0; kb <= PRE2; kb++) load_stage(sb, kb, b, m);
  } else if (tid >= T_PF && tid < T_PF + 12) {
    tm_prefetch(&m.x + (tid - T_PF));
  } else if (tid == T_INIT) {
#pragma unroll
    for (int i = 0; i < 4; i++) mbar_init(bars + 8 * (B_EMPTY1 + i), 8);
#pragma unroll
    for (int i = 0; i < 8; i++) mbar_init(bars + 8 * (B_FULL2 + i), 1);
#pragma unroll
    for (int i = 0; i < 4; i++) mbar_init(bars + 8 * (B_EMPTY2 + i), 8);
#pragma unroll
    for (int i = 0; i < 4; i++) mbar_init(bars + 8 * (B_U + i), 1);
    mbar_init(bars + 8 * B_HA, 4);
    mbar_init(bars + 8 * B_GATE, 4);
    mbar_init(bars + 8 * B_HB, 1);
    mbar_init(bars + 8 * B_KVD, 4);
    mbar_init(bars + 8 * B_QF, 1);
    mbar_init(bars + 8 * B_ATTN, 8);
    mbar_init(bars + 8 * B_P1, 8);
    mbar_init(bars + 8 * B_C34, 1);
#pragma unroll
    for (int i = 0; i < 5; i++) mbar_init(bars + 8 * (B_YST + i), 4);
#pragma unroll
    for (int i = 0; i < 5; i++) mbar_init(bars + 8 * (B_US + i), 4);
    mbar_init(bars + 8 * B_YSIG, 1);
    mbar_init(bars + 8 * B_YFULL, 1);
    mbar_init(bars + 8 * B_EPOCH, 1);
    mbar_init(bars + 8 * B_PREP, 4);
    mbar_init(bars + 8 * B_USIG, 1);
    mbar_init(bars + 8 * B_WST, 1);
#pragma unroll
    for (int i = 3; i < 5; i++) mbar_init(bars + 8 * (B_KV + i), 1);
    mbar_init(bars + 8 * B_E3, 8);
    mbar_init(bars + 8 * B_LAST, 1);
    mbar_init(bars + 8 * B_OSIG, 1);
    mbar_init(bars + 8 * B_WOP, 1);
    fence_async_smem();
  }
  const int warp = __shfl_sync(0xffffffffu, tid >> 5, 0), wg = warp >> 2, w = warp & 3;
  __syncthreads();

  if (wg == 3) {
    asm volatile("setmaxnreg.dec.sync.aligned.u32 56;");
    if (w == 0) {
      if (lane == 0) {
#pragma unroll 1
        for (int kb = 1 + PRE2; kb < 10; kb++) {
          if (kb >= 4) mbar_wait(bars + 8 * (kb == 7 ? B_E3 : B_EMPTY1 + (kb & 3)), (kb >> 3) & 1);
          TSIF(kb >= 4, 44 + kb);
          load_stage(sb, kb, b, m);
          TSIF(kb == 3, 60);
          if (kb == TRIG_KB) mbar_arrive(bars + 8 * B_LAST);
        }
        mbar_wait(bars + 8 * B_WOP, 0);
        mbar_wait(bars + 8 * WL_TRIG, 0);
        mbar_wait(bars + 8 * B_EPOCH, 0);
        flag_wait(g_cnt + C_W + 32 * hg, (lds32(sb + OFF_EPOCH) + 1) * 16);
        TS(30);
#pragma unroll 1
        for (int j = 0; j < 8; j++) {
          if (j >= 6) mbar_wait(bars + 8 * (B_EMPTY2 + j - 6), 0);
          if (j == 4) mbar_wait(bars + 8 * B_ATTN, 0);
          TSIF(j >= 6, 100 + j);
          if (RF_GATE && j == 6) mbar_wait(bars + 8 * B_YSIG, 0);
          mbar_expect_tx(bars + 8 * (B_FULL2 + j), j == 0 ? WO_BYTES : j == 5 ? O_BYTES + WO_BYTES + 512 : O_BYTES + WO_BYTES);
          bulk_load(sb + off_w(j), g_WO + (hg * 8 + step_src(hg, j)) * 800, WO_BYTES, bars + 8 * (B_FULL2 + j));
        }
        mbar_wait(bars + 8 * (B_EMPTY2 + 3), 0);
        mbar_expect_tx(bars + 8 * B_QF, O_BYTES);
        tma_2d(sb + OFF_QS, &m.qm, 80 * hg, 128 * r, bars + 8 * B_QF);
        tma_2d(sb + OFF_QT, &m.qt, 80 * hg + 64, 128 * r, bars + 8 * B_QF);
      }
    } else if (w == 1) {
      unsigned epoch = 0;
      if (lane == 0) {
        epoch = atomicAdd(g_cnt + C_LAUNCH, 1u) / NCTA;
        asm volatile("st.shared.u32 [%0], %1;" ::"r"(sb + OFF_EPOCH), "r"(epoch) : "memory");
        mbar_arrive(bars + 8 * B_EPOCH);
        mbar_wait(bars + 8 * B_KVD, 0);
        mbar_expect_tx(bars + 8 * B_HB, 5 * 4096);
#pragma unroll 1
        for (int c = 0; c < 5; c++) {
          if (c == 3) mbar_wait(bars + 8 * B_S3, 0);
          bulk_load(sb + off_ch(c) + U_BYTES, p.ssm_k + (5 * b + c) * SEQ, 4096, bars + 8 * B_HB);
        }
#pragma unroll
        for (int c = 0; c < 4; c++) mbar_expect_tx(bars + 8 * (B_U + c), c < 3 ? U_BYTES : 2 * U_BYTES);
        const uint4* usrc = g_U + 5 * b * U_PITCH;
        mbar_wait(bars + 8 * B_USIG, 0);
        flag_wait(g_cnt + C_PREP + 32 * (b & 15), (epoch + 1) * NCTA);
        TS(23);
#pragma unroll
        for (int c = 0; c < 5; c++) {
          if (c == 3) mbar_wait(bars + 8 * (B_U + 2), 0);
          bulk_load(sb + off_ch(c), usrc + c * U_PITCH, U_BYTES, bars + 8 * (B_U + (c < 3 ? c : 3)));
          TSIF(c == 0 || c == 4, 116 + (c >> 2));
        }
      }
      epoch = __shfl_sync(0xffffffffu, epoch, 0);
      if (lane < 8) {
        const int src = (b & ~7) | step_src(hg, lane);
        mbar_wait(bars + 8 * B_OSIG, 0);
        TS(20);
        flag_wait(g_cnt + C_O + 32 * src, epoch + 1);
        if (lane >= 1 && lane < 4) bulk_load(sb + off_o(lane), g_O + src * 1280, O_BYTES, bars + 8 * (B_FULL2 + lane));
        __syncwarp(0xff);
        TS(21);
        if (lane == 5) bulk_load(sb + OFF_GATE, g_gate + 128 * r, 512, bars + 8 * (B_FULL2 + 5));
#pragma unroll 1
        for (int j = 4; j < 8; j++) {
          if (lane == j) {
            mbar_wait(bars + 8 * (j < 6 ? B_C34 : B_EMPTY2 + j - 6), 0);
            if (RF_GATE && j == 6) mbar_wait(bars + 8 * B_YSIG, 0);
            bulk_load(sb + off_o(j), g_O + src * 1280, O_BYTES, bars + 8 * (B_FULL2 + j));
          }
          __syncwarp(0xff);
        }
        TS(22);
      }
    } else if (w == 2) {
      mbar_wait(bars + 8 * B_PREP, 0);
      flag_signal(g_cnt + C_PREP, 16, lane);
      TS(25);
      if (lane == 0) mbar_arrive(bars + 8 * B_USIG);
      mbar_wait(bars + 8 * B_GATE, 0);
      if ((NOMB & 1) && lane == 0) asm volatile("fence.release.gpu;" ::: "memory");
      mbar_wait(bars + 8 * B_ATTN, 0);
      if (lane == 0) {
        if (O_DEFER) mbar_wait(bars + 8 * (B_U + 3), 0);
        asm volatile("cp.async.bulk.global.shared::cta.bulk_group [%0], [%1], 20480;\ncp.async.bulk.commit_group;\n"
                     "cp.async.bulk.wait_group 0;\nfence.proxy.async.global;" ::"l"(g_O + b * 1280), "r"(sb + OFF_OA) : "memory");
      }
      TS(74);
      if (!(NOMB & 1)) flag_signal(g_cnt + C_O + 32 * b, 1, lane);
      else if (lane == 0) flag_bump(g_cnt + C_O + 32 * b);
      TS(26);
      if (lane == 0) mbar_arrive(bars + 8 * B_OSIG);

    } else {
      if (lane == 0) {
        uint4* dst = g_WO + (hg * 8 + (r >> 1)) * 800 + (r & 1) * 80;
        mbar_wait(bars + 8 * B_P1, 0);
        mbar_wait(bars + 8 * WB_TRIG, 0);
        mbar_expect_tx(bars + 8 * B_WST, WO_BYTES / 2);
        tma_3d(sb + OFF_WS, &m.wo, 0, 40 * r, 5 * hg, bars + 8 * B_WST);
        mbar_wait(bars + 8 * B_WST, 0);
        mbar_wait(bars + 8 * WO_TRIG, 0);
#pragma unroll 1
        for (int n = 0; n < 5; n++)
          asm volatile("cp.async.bulk.global.shared::cta.bulk_group [%0], [%1], 1280;" ::"l"(dst + 160 * n), "r"(sb + OFF_WS + 1280 * n) : "memory");
        asm volatile("cp.async.bulk.commit_group;\ncp.async.bulk.wait_group 0;\nfence.proxy.async.global;" ::: "memory");
        if (!(NOMB & 4)) asm volatile("fence.release.gpu;" ::: "memory");
        flag_bump(g_cnt + C_W + 32 * hg);
        mbar_arrive(bars + 8 * B_WOP);
        TS(71);
#pragma unroll 1
        for (int c = 0; c < 5; c++) {
          mbar_wait(bars + 8 * (B_YST + c), 0);
          asm volatile("cp.async.bulk.global.shared::cta.bulk_group [%0], [%1], 4096;\ncp.async.bulk.commit_group;"
                       ::"l"(g_Y + (5 * b + c) * Y_PITCH), "r"(sb + off_ch(c)) : "memory");
          if (c == 2) {
            asm volatile("cp.async.bulk.wait_group.read 0;" ::: "memory");
            mbar_arrive(bars + 8 * B_C34);
          }
        }
        asm volatile("cp.async.bulk.wait_group 0;\nfence.proxy.async.global;" ::: "memory");
        TS(75);
        if (!(NOMB & 2)) asm volatile("fence.release.gpu;" ::: "memory");
        flag_bump(g_cnt + C_Y + 32 * (b >> 4));
        TS(27);
        mbar_arrive(bars + 8 * B_YSIG);
        mbar_expect_tx(bars + 8 * B_YFULL, 20480);
        flag_wait(g_cnt + C_Y + 32 * hg, (lds32(sb + OFF_EPOCH) + 1) * 16);
        TS(24);
        tma_2d(sb + OFF_YT, &m.y, 128 * r, 80 * hg, bars + 8 * B_YFULL);
        tma_2d(sb + OFF_YT + 10240, &m.y, 128 * r + 64, 80 * hg, bars + 8 * B_YFULL);
      }
    }
  } else {
    asm volatile("setmaxnreg.inc.sync.aligned.u32 152;");
    if (wg < 2) {
      float acc[120];
#pragma unroll
      for (int i = 0; i < 120; i++) acc[i] = 0.f;
      const uint32_t da = desc_lo(sb + wg * 8192, 16), db = desc_lo(sb + ST_W, 8192), dc = desc_lo(sb + ST_WT, 2048);
      if (PW1) pin<120>(acc);
      if (PW1 == 2) mbar_wait(bars + 8 * B_FULL1, 0);
#pragma unroll 1
      for (int kb = 0; kb < 10; kb++) {
        mbar_wait(bars + 8 * (B_FULL1 + (kb & 3)), (kb >> 2) & 1);
        const uint32_t so = (kb & 3) * (STAGE_BYTES >> 4);
        wg_fence();
#pragma unroll
        for (int k = 0; k < 4; k++) {
          WgSST<192>::mma<HI_SW128, HI_SW128>(acc, da + so + 2 * k, db + so + 128 * k, 1);
          WgSST<48>::mma<HI_SW128, HI_SW32>(acc + 96, da + so + 2 * k, dc + so + 32 * k, 1);
        }
        wg_commit();
        wg_wait<1>();
        if (kb > 0 && lane == 0) mbar_arrive(bars + 8 * (kb == 4 ? B_E3 : B_EMPTY1 + ((kb - 1) & 3)));
      }
      mbar_wait(bars + 8 * B_EPOCH, 0);
      const uint32_t tag = lds32(sb + OFF_EPOCH) + 1;
      mbar_wait(bars + 8 * B_S3, 0);
      wg_wait<0>();
      pin<120>(acc);
      if (lane == 0) mbar_arrive(bars + 8 * B_P1);
      TSM(w == 0, 3 + wg);
      attention(acc, sb, b, wg, w, lane, tag);
    } else {
      const int tw = tid & 127, chl = 64 * (b & 1) + 8 * w + (lane >> 2);
      uint4* up = g_U + chl * U_PITCH + ((4 * (b >> 1) + (lane & 3)) ^ ((b >> 2) & 1));
      uint2 sw[10];
      uint32_t dv = 0;
      if (lane < 5) dv = __ldg(reinterpret_cast<const unsigned short*>(p.ssm_D) + 5 * b + lane);
#pragma unroll
      for (int i = 0; i < 10; i++) sw[i] = ldg64(reinterpret_cast<const uint2*>(p.shift_k) + chl + 128 * (i >> 1) + 32 * (i & 1));
      uint32_t tab[12];
      float tt[4];
      fft_tables(tab, tw);
      fft_twiddles(tt, tw);
      uint4 res[10];
#pragma unroll
      for (int i = 0; i < 10; i++) res[i] = make_uint4(0, 0, 0, 0);
#pragma unroll 1
      for (int slab = 0; slab < 5; slab++) {
#pragma unroll
        for (int i = 0; i < 8; i++) res[i] = res[i + 2];
        prep_slab(res + 8, sw, sb, slab, w, lane);
        TSIF(w == 0, 99 + 4 * slab);
#pragma unroll
        for (int i = 0; i < 8; i++) sw[i] = sw[i + 2];
      }
      TSIF(w == 0, 28);
      __syncwarp();
      if (lane == 0) mbar_arrive(bars + 8 * B_KVD + ((res[8].x ^ res[9].x) & p.zero));
      mbar_wait(bars + 8 * B_KVD, 0);
      fft_tables_store(tab, sb, tw);
      mbar_wait(bars + 8 * B_LAST, 0);
#pragma unroll
      for (int i = 0; i < 10; i++) up[(128 * (i >> 1) + 32 * (i & 1)) * U_PITCH] = res[i];
      __syncwarp();
      if (lane == 0) mbar_arrive(bars + 8 * B_PREP);
      TSIF(w == 0 && !U_TMA, 5);
      mbar_wait(bars + 8 * (G_AFTER ? B_USIG : B_LAST), 0);
      prep_gate(p, b, w, lane);
      __syncwarp();
      if (lane == 0) mbar_arrive(bars + 8 * B_GATE);
      TSIF(w == 0, 72);
      mbar_wait(bars + 8 * B_HB, 0);
      TSIF(w == 0, 2);
      const uint32_t ha = sb + U_BYTES + ((tw >> 3) * 16 + 8 + (tw & 7)) * 16;
      uint4 hv[5];
#pragma unroll
      for (int c = 0; c < 5; c++) hv[c] = lds128(ha + off_ch(c));
      __syncwarp();
#pragma unroll
      for (int c = 0; c < 5; c++) sts128((ha ^ 16) + off_ch(c), hv[c].x, hv[c].y, hv[c].z, hv[c].w);
      sts128(sb + OFF_TT + 16 * tw, __float_as_uint(tt[0]), __float_as_uint(tt[1]), __float_as_uint(tt[2]), __float_as_uint(tt[3]));
      if (tw < 5) asm volatile("st.shared.f32 [%0], %1;" ::"r"(sb + OFF_D + 4 * tw), "f"(bf_lo(dv) * 0.125f) : "memory");
      fence_async_smem();
      __syncwarp();
      if (lane == 0) mbar_arrive(bars + 8 * B_HA);
      TSIF(w == 0, 6);
    }

    FftConst fc;
    TSM(w == 0 && wg == 0, 104);
    mbar_wait(bars + 8 * B_HA, 0);
    fft_matrices(fc, sb, w, lane);
    TSM(w == 0 && wg == 0, 105);
    if (ATT_GATE && !H_EARLY) mbar_wait(bars + 8 * B_ATTN, 0);
    TSM(w == 0 && wg == 2, 124);
#pragma unroll 1
    for (int c = wg == 2 ? 0 : wg + 1; c < 5; c += !CH_W2 ? 3 : wg < 2 ? 5 : c ? 1 : 3) {
      conv_channel(fc, sb, c, wg, w, lane);
      if (lane == 0) mbar_arrive(bars + 8 * (B_YST + c));
      TSM(w == 0, 10 + c);
    }

    if (wg < 2) {
      const int g = lane >> 2;
      float acc[40];
#pragma unroll
      for (int i = 0; i < 40; i++) acc[i] = 0.f;
      const uint32_t da = desc_lo(sb + wg * 1024, 2048), db = desc_lo(sb, 2560);
      mbar_wait(bars + 8 * B_ATTN, 0);
      mbar_wait(bars + 8 * (B_YST + 3), 0);
      mbar_wait(bars + 8 * (B_YST + 4), 0);
      if (PW2) mbar_wait(bars + 8 * B_FULL2, 0);
      TSM(w == 0, 15 + wg);
#pragma unroll 1
      for (int j = 0; j < 8; j++) {
        mbar_wait(bars + 8 * (B_FULL2 + j), 0);
        const uint32_t oa = da + (off_o(j) >> 4), ob = db + (off_w(j) >> 4);
        wg_fence();
#pragma unroll
        for (int k = 0; k < 5; k++) WgSST<80>::mma<HI_NONE, HI_SW32>(acc, oa + 256 * k, ob + 32 * k, 1);
        wg_commit();
        wg_wait<1>();
        if (j >= 1 && j <= 4 && lane == 0) mbar_arrive(bars + 8 * (B_EMPTY2 + j - 1));
      }
      TSIF(w == 0 && wg == 0, 113);
      const int tr = 64 * wg + 16 * w + (lane & 15);
      const uint32_t fm = sb + OFF_QS + tr * 128, fx = (lane >> 4) ^ (tr & 7);
      const uint32_t ft = sb + OFF_QT + tr * 32 + (((lane >> 4) ^ (tr >> 2)) & 1) * 16;
      const float g0 = __uint_as_float(lds32(sb + OFF_GATE + (64 * wg + 16 * w + g) * 4));
      const float g1 = __uint_as_float(lds32(sb + OFF_GATE + (64 * wg + 16 * w + 8 + g) * 4));
      const uint32_t ga = pack2(g0, g0), gb = pack2(g1, g1);
      const uint32_t na = pack2(1.f - g0, 1.f - g0), nb = pack2(1.f - g1, 1.f - g1);

      wg_wait<0>();
      pin<40>(acc);
      TSM(w == 0, 17 + wg);
      uint32_t pb[20];
#pragma unroll
      for (int j = 0; j < 10; j++) {
        pb[2 * j] = bmul(na, pack2(acc[4 * j], acc[4 * j + 1]));
        pb[2 * j + 1] = bmul(nb, pack2(acc[4 * j + 2], acc[4 * j + 3]));
        asm volatile("" : "+r"(pb[2 * j]), "+r"(pb[2 * j + 1]));
      }
      const uint32_t ya = sb + OFF_YT + wg * 10240 + ((lane >> 4) * 8 + (lane & 7)) * 128 +
                          (((2 * w + (((lane >> 3) & 1) ^ wg)) ^ (lane & 7)) << 4);
      uint32_t qf[20];
      mbar_wait(bars + 8 * B_QF, 0);
#pragma unroll
      for (int j = 0; j < 5; j++) ldsm4(qf + 4 * j, j < 4 ? fm + ((fx ^ (2 * j)) << 4) : ft);
      mbar_wait(bars + 8 * B_YFULL, 0);
      TSM(w == 0 && wg == 0, 19);
#pragma unroll
      for (int j = 0; j < 5; j++) {
        uint32_t y[4];
        ldsm4t(y, ya + 2048 * j);
#pragma unroll
        for (int i = 0; i < 4; i++) qf[4 * j + i] = badd(bmul((i & 1) ? gb : ga, bmul(qf[4 * j + i], y[i])), pb[4 * j + i]);
      }
#pragma unroll
      for (int j = 0; j < 5; j++) stsm4(j < 4 ? fm + ((fx ^ (2 * j)) << 4) : ft, qf + 4 * j);
      fence_async_smem();
      __syncwarp();
      if (lane == 0) {
        const int row = 64 * wg + 16 * w;
        asm volatile("cp.async.bulk.tensor.2d.global.shared::cta.bulk_group [%0, {%2, %3}], [%1];"
                     ::"l"(&m.om), "r"(sb + OFF_QS + row * 128), "r"(80 * hg), "r"(128 * r + row) : "memory");
        asm volatile("cp.async.bulk.tensor.2d.global.shared::cta.bulk_group [%0, {%2, %3}], [%1];"
                     ::"l"(&m.ot), "r"(sb + OFF_QT + row * 32), "r"(80 * hg + 64), "r"(128 * r + row) : "memory");
        asm volatile("cp.async.bulk.commit_group;\ncp.async.bulk.wait_group.read 0;" ::: "memory");
      }
      TSM(true, 40 + 4 * wg + w);
      if (ENDBAR) asm volatile("bar.sync 15, 256;" ::: "memory");
    }
  }
}

typedef CUresult (*EncodeFn)(CUtensorMap*, CUtensorMapDataType, cuuint32_t, void*, const cuuint64_t*, const cuuint64_t*,
                             const cuuint32_t*, const cuuint32_t*, CUtensorMapInterleave, CUtensorMapSwizzle,
                             CUtensorMapL2promotion, CUtensorMapFloatOOBfill);

void encode(EncodeFn fn, CUtensorMap* tm, const void* base, int rank, const cuuint64_t* dims, const cuuint64_t* strides,
            const cuuint32_t* box, CUtensorMapSwizzle swz) {
  const cuuint32_t ones[3] = {1, 1, 1};
  fn(tm, CU_TENSOR_MAP_DATA_TYPE_BFLOAT16, rank, const_cast<void*>(base), dims, strides, box, ones,
     CU_TENSOR_MAP_INTERLEAVE_NONE, swz, CU_TENSOR_MAP_L2_PROMOTION_L2_128B, CU_TENSOR_MAP_FLOAT_OOB_FILL_NONE);
}

}

extern "C" void kernel_launch(void* const* d_in, const int* in_sizes, int n_in, void* d_out, int out_size) {
  (void)in_sizes; (void)n_in; (void)out_size;
  Params p;
  p.q = (const __nv_bfloat16*)d_in[0];
  p.k = (const __nv_bfloat16*)d_in[1];
  p.v = (const __nv_bfloat16*)d_in[2];
  p.shift_k = (const __nv_bfloat16*)d_in[3];
  p.ssm_k = (const __nv_bfloat16*)d_in[4];
  p.ssm_D = (const __nv_bfloat16*)d_in[5];
  p.wqkv = (const __nv_bfloat16*)d_in[7];
  p.wo = (const __nv_bfloat16*)d_in[8];
  p.gate_w = (const __nv_bfloat16*)d_in[9];
  p.out = (__nv_bfloat16*)d_out;
  p.zero = 0;

  static EncodeFn fn = nullptr;
  static void *yaddr = nullptr, *uaddr = nullptr;
  if (!fn) {
    cudaDriverEntryPointQueryResult qr;
    void* f = nullptr;
    cudaGetDriverEntryPoint("cuTensorMapEncodeTiled", &f, cudaEnableDefault, &qr);
    fn = (EncodeFn)f;
    cudaGetSymbolAddress(&yaddr, g_Y);
    cudaGetSymbolAddress(&uaddr, g_U);
    cudaFuncSetAttribute(fused_kernel, cudaFuncAttributeMaxDynamicSharedMemorySize, SMEM_BYTES);
  }
  Maps m;
  {
    const cuuint64_t dims[3] = {640, 1024, 2}, st[2] = {2560, 1280};
    const cuuint32_t box[3] = {64, 64, 2};
    encode(fn, &m.x, p.q, 3, dims, st, box, CU_TENSOR_MAP_SWIZZLE_128B);
  }
  {
    const cuuint64_t dims[3] = {640, 640, 3}, st[2] = {3840, 1280};
    const cuuint32_t box[3] = {64, 64, 3}, boxt[3] = {16, 64, 3};
    encode(fn, &m.wm, p.wqkv, 3, dims, st, box, CU_TENSOR_MAP_SWIZZLE_128B);
    encode(fn, &m.wt, p.wqkv, 3, dims, st, boxt, CU_TENSOR_MAP_SWIZZLE_32B);
  }
  {
    const cuuint64_t dims[3] = {64, 2048, 10}, st[2] = {1280, 128};
    const cuuint32_t boxk[3] = {64, 35, 1}, boxv[3] = {64, 32, 1};
    encode(fn, &m.k, p.k, 3, dims, st, boxk, CU_TENSOR_MAP_SWIZZLE_128B);
    encode(fn, &m.v, p.v, 3, dims, st, boxv, CU_TENSOR_MAP_SWIZZLE_128B);
  }
  {
    const cuuint64_t dims[3] = {16, 640, 40}, st[2] = {1280, 32};
    const cuuint32_t box[3] = {16, 40, 5};
    encode(fn, &m.wo, p.wo, 3, dims, st, box, CU_TENSOR_MAP_SWIZZLE_32B);
  }
  {
    const cuuint64_t dims[2] = {2048, 640}, st[1] = {Y_PITCH * 16};
    const cuuint32_t box[2] = {64, 80};
    encode(fn, &m.y, yaddr, 2, dims, st, box, CU_TENSOR_MAP_SWIZZLE_128B);
    const cuuint64_t stu[1] = {U_PITCH * 16};
    const cuuint32_t boxu[2] = {32, 64};
    encode(fn, &m.u, uaddr, 2, dims, stu, boxu, CU_TENSOR_MAP_SWIZZLE_NONE);
  }
  {
    const cuuint64_t dims[2] = {640, 2048}, st[1] = {1280};
    const cuuint32_t bqm[2] = {64, 128}, bqt[2] = {16, 128}, bom[2] = {64, 16}, bot[2] = {16, 16};
    encode(fn, &m.qm, p.q, 2, dims, st, bqm, CU_TENSOR_MAP_SWIZZLE_128B);
    encode(fn, &m.qt, p.q, 2, dims, st, bqt, CU_TENSOR_MAP_SWIZZLE_32B);
    encode(fn, &m.om, p.out, 2, dims, st, bom, CU_TENSOR_MAP_SWIZZLE_128B);
    encode(fn, &m.ot, p.out, 2, dims, st, bot, CU_TENSOR_MAP_SWIZZLE_32B);
  }
  fused_kernel<<<NCTA, NTHR, SMEM_BYTES>>>(m, p);
}
```

```cpp
#include <cuda.h>
#include <cuda_bf16.h>
#include <cuda_runtime.h>
#include <stdint.h>

namespace {

constexpr int SEQ = 2048, DIM = 640, NCTA = 128, NTHR = 512;

#define TRIG_KB 9
#define KV_KB 2
#define DEV_EXIT 0
#define ATT_GATE 1
#define G_AFTER 0
#define FENCE_LO 0
#define FENCE_HI 0
#define PW1 2
#define PW2 1
#define ENDBAR 0
#define PAD_KB 0
#define Y_ALIAS 1
#define H_EARLY 1
#define NOMB 0
#define SRC_ROT 0
#define WAIT_NS 0
#define WB_TRIG B_USIG
#define G_POS 0
#define TAILF 1
#define T_ISSUE 384
#define T_PF 416
#define T_INIT 448
#define ATT_MERGE 0
#define BMAP 1
#define PRE2 1
#define KV_MIX 0
#define O_DEFER 0
#define CH_W2 0
#define HALO_FIRST 1
#define PREV_EARLY 0
#define SLEEP_NS 1000
#define SLEEP_P1 0
#define ACQ 0
#define U_TMA 0
#define U_GATE 0
#define RF_GATE 0
#define WO_TRIG B_WST
#define WL_TRIG B_WOP
#define WO_GATE 1

constexpr uint32_t STAGE_BYTES = 47104, ST_W = 16384, ST_WT = 40960;
constexpr uint32_t O_BYTES = 20480, WO_BYTES = 12800;
constexpr uint32_t OFF_OA = 0;
constexpr uint32_t OFF_QS = 3 * O_BYTES, OFF_QT = OFF_QS + 16384;
constexpr uint32_t OFF_WC = 81920;
constexpr uint32_t OFF_WA = 94720;
constexpr uint32_t OFF_GATE = 145920;
constexpr uint32_t OFF_TT = 146432;
constexpr uint32_t OFF_KVX = 148480;
constexpr uint32_t OFF_CH3 = 163840;
constexpr uint32_t CH_BYTES = 12288, U_BYTES = 4096;
constexpr uint32_t OFF_FT = 225280, OFF_GT = 229376;
constexpr uint32_t OFF_CH0 = 188416;
constexpr uint32_t OFF_KVS = OFF_CH0, KVS_V = 4480, KVS_BYTES = 8576;
constexpr uint32_t OFF_WS = OFF_WA;
__device__ __forceinline__ uint32_t off_us(int s) { return OFF_CH0 + 4096 * ((0x65320 >> (4 * s)) & 7); }
constexpr uint32_t OFF_YT = 163840;
constexpr uint32_t OFF_BAR = 231936;
constexpr uint32_t SMEM_BYTES = OFF_BAR + 512;

enum : uint32_t {
  B_FULL1 = 0, B_EMPTY1 = 4, B_S3 = 7, B_FULL2 = 52, B_EMPTY2 = 13, B_U = 8, B_GATE = 12, B_HA = 19, B_HB = 20,
  B_ATTN = 21, B_C34 = 22, B_CONV = 23, B_YFULL = 24, B_EPOCH = 25, B_PREP = 26, B_P1 = 27, B_LAST = 28,
  B_E3 = 29, B_OSIG = 30, B_WOP = 31, B_USIG = 32, B_WST = 33, B_KV = 34, B_KVD = 39, B_QF = 17, B_YST = 40,
  B_US = 45, B_YSIG = 50
};
constexpr uint32_t OFF_EPOCH = OFF_BAR + 8 * 51, OFF_D = OFF_BAR + 8 * 60;
__device__ __forceinline__ uint32_t off_o(int j) { return j < 4 ? OFF_OA + j * O_BYTES : j < 6 ? OFF_CH0 + (j - 4) * O_BYTES : OFF_OA + (j - 6) * O_BYTES; }
__device__ __forceinline__ uint32_t off_w(int j) { return j < 4 ? OFF_WA + j * WO_BYTES : j == 4 ? OFF_KVX : j == 5 ? OFF_WC : OFF_WA + (j - 6) * WO_BYTES; }
__device__ __forceinline__ int step_src(int hg, int j) { return SRC_ROT ? (hg + j) & 7 : j == 0 ? hg : j <= hg ? j - 1 : j; }
__device__ __forceinline__ bool tail_first(int hg) { return TAILF && (hg & 3) == 3; }
__device__ __forceinline__ uint32_t off_ch(int c) { return (c < 3 ? OFF_CH0 : OFF_CH3 - 3 * CH_BYTES) + c * CH_BYTES; }

#define U_PITCH 264
__device__ __align__(1024) uint4 g_U[DIM * U_PITCH];
__device__ uint4 g_O[NCTA * 1280];
#define g_Y g_U
constexpr int Y_PITCH = U_PITCH;
__device__ uint4 g_WO[64 * 800];
__device__ uint4 g_halo[NCTA * 2 * 7 * 32];
__device__ float g_gate[SEQ + PAD_KB * 256];
__device__ unsigned g_cnt[32 * (1 + 2 * 16 + 8 + NCTA)];
constexpr int C_LAUNCH = 0, C_PREP = 32, C_Y = 32 * 17, C_W = 32 * 33, C_O = 32 * 41;

#define TSM(cond, slot) do { } while (0)
#define TSIF(cond, slot) do { if (__LINE__ >= FENCE_LO && __LINE__ < FENCE_HI) sched_fence(); } while (0)
__device__ __forceinline__ void sched_fence() {
  asm volatile("{\n.reg .pred p;\n.reg .u32 c;\nmov.u32 c, %%clock;\nsetp.eq.u32 p, c, 0;\n@p st.shared.u32 [%0], c;\n}"
               ::"r"(1024 + OFF_EPOCH + 4) : "memory");
}
#define TS(slot) TSIF(true, slot)

struct Params {
  const __nv_bfloat16 *q, *k, *v, *shift_k, *ssm_k, *ssm_D, *wqkv, *wo, *gate_w;
  __nv_bfloat16* out;
  uint32_t zero;
};

#define POLL_NS 0
constexpr int SPIN_LIMIT = 1 << 17;

__device__ __forceinline__ void mbar_init(uint32_t bar, uint32_t count) {
  asm volatile("mbarrier.init.shared::cta.b64 [%0], %1;" ::"r"(bar), "r"(count) : "memory");
}
__device__ __forceinline__ void mbar_expect_tx(uint32_t bar, uint32_t bytes) {
  asm volatile("mbarrier.arrive.expect_tx.shared::cta.b64 _, [%0], %1;" ::"r"(bar), "r"(bytes) : "memory");
}
__device__ __forceinline__ void mbar_arrive(uint32_t bar) {
  asm volatile("mbarrier.arrive.shared::cta.b64 _, [%0];" ::"r"(bar) : "memory");
}
__device__ __forceinline__ void mbar_wait(uint32_t bar, uint32_t parity) {
  uint32_t ok;
  int spins = 0;
  do {
    if (WAIT_NS)
      asm volatile("{\n.reg .pred p;\nmbarrier.try_wait.parity.shared::cta.b64 p, [%1], %2, %3;\nselp.b32 %0, 1, 0, p;\n}"
                   : "=r"(ok) : "r"(bar), "r"(parity), "r"(WAIT_NS) : "memory");
    else
      asm volatile("{\n.reg .pred p;\nmbarrier.try_wait.parity.shared::cta.b64 p, [%1], %2;\nselp.b32 %0, 1, 0, p;\n}"
                   : "=r"(ok) : "r"(bar), "r"(parity) : "memory");
    if (++spins > SPIN_LIMIT) break;
  } while (!ok);
}
__device__ __forceinline__ void mbar_sleep(uint32_t bar, uint32_t parity) {
  uint32_t ok;
  int spins = 0;
  do {
    if (SLEEP_NS)
      asm volatile("{\n.reg .pred p;\nmbarrier.try_wait.parity.shared::cta.b64 p, [%1], %2, %3;\nselp.b32 %0, 1, 0, p;\n}"
                   : "=r"(ok) : "r"(bar), "r"(parity), "r"(SLEEP_NS) : "memory");
    else
      asm volatile("{\n.reg .pred p;\nmbarrier.try_wait.parity.shared::cta.b64 p, [%1], %2;\nselp.b32 %0, 1, 0, p;\n}"
                   : "=r"(ok) : "r"(bar), "r"(parity) : "memory");
    if (++spins > SPIN_LIMIT) break;
  } while (!ok);
}
__device__ __forceinline__ void flag_poll(const unsigned* p, unsigned target) {
  unsigned v;
  int spins = 0;
  do {
    if (POLL_NS && spins) __nanosleep(POLL_NS);
    asm volatile("ld.relaxed.gpu.global.u32 %0, [%1];" : "=r"(v) : "l"(p) : "memory");
    if (++spins > SPIN_LIMIT) break;
  } while ((int)(v - target) < 0);
}
__device__ __forceinline__ void flag_wait(const unsigned* p, unsigned target) {
  flag_poll(p, target);
  if (ACQ) asm volatile("fence.acquire.gpu;\nfence.proxy.async.global;" ::: "memory");
}
__device__ __forceinline__ void flag_signal(unsigned* p, int n, int lane) {
  if (lane == 0) asm volatile("fence.release.gpu;" ::: "memory");
  __syncwarp();
  if (lane < n) asm volatile("red.relaxed.gpu.global.add.u32 [%0], 1;" ::"l"(p + 32 * lane) : "memory");
}
__device__ __forceinline__ void flag_bump(unsigned* p) {
  asm volatile("red.relaxed.gpu.global.add.u32 [%0], 1;" ::"l"(p) : "memory");
}
__device__ __forceinline__ void fence_async_smem() { asm volatile("fence.proxy.async.shared::cta;" ::: "memory"); }
__device__ __forceinline__ void wg_sync(int id) { asm volatile("bar.sync %0, 128;" ::"r"(id) : "memory"); }

__device__ __forceinline__ void tma_2d(uint32_t dst, const CUtensorMap* tm, int c0, int c1, uint32_t bar) {
  asm volatile("cp.async.bulk.tensor.2d.shared::cluster.global.mbarrier::complete_tx::bytes [%0], [%1, {%3, %4}], [%2];"
               ::"r"(dst), "l"(tm), "r"(bar), "r"(c0), "r"(c1) : "memory");
}
__device__ __forceinline__ void tma_3d(uint32_t dst, const CUtensorMap* tm, int c0, int c1, int c2, uint32_t bar) {
  asm volatile("cp.async.bulk.tensor.3d.shared::cluster.global.mbarrier::complete_tx::bytes [%0], [%1, {%3, %4, %5}], [%2];"
               ::"r"(dst), "l"(tm), "r"(bar), "r"(c0), "r"(c1), "r"(c2) : "memory");
}
__device__ __forceinline__ void bulk_load(uint32_t dst, const void* src, uint32_t bytes, uint32_t bar) {
  asm volatile("cp.async.bulk.shared::cluster.global.mbarrier::complete_tx::bytes [%0], [%1], %2, [%3];"
               ::"r"(dst), "l"(src), "r"(bytes), "r"(bar) : "memory");
}
__device__ __forceinline__ void tm_prefetch(const CUtensorMap* tm) {
  asm volatile("prefetch.tensormap [%0];" ::"l"(tm) : "memory");
}

__device__ __forceinline__ void wg_fence() { asm volatile("wgmma.fence.sync.aligned;" ::: "memory"); }
__device__ __forceinline__ void wg_commit() { asm volatile("wgmma.commit_group.sync.aligned;" ::: "memory"); }
template <int N> __device__ __forceinline__ void wg_wait() { asm volatile("wgmma.wait_group.sync.aligned %0;" ::"n"(N) : "memory"); }
__device__ __forceinline__ uint32_t desc_lo(uint32_t addr, uint32_t lbo) { return ((addr & 0x3FFFF) >> 4) | ((lbo >> 4) << 16); }
constexpr uint32_t desc_hi(uint32_t sbo, uint32_t swz) { return (sbo >> 4) | (swz << 30); }
constexpr uint32_t HI_SW128 = desc_hi(1024, 1), HI_SW64 = desc_hi(512, 2), HI_SW32 = desc_hi(256, 3), HI_NONE = desc_hi(128, 0);
template <int N> __device__ __forceinline__ void pin(float* d) {
#pragma unroll
  for (int i = 0; i < N; i++) asm volatile("" : "+f"(d[i])::"memory");
}

__device__ __forceinline__ uint32_t lds32(uint32_t a) {
  uint32_t v;
  asm volatile("ld.volatile.shared.u32 %0, [%1];" : "=r"(v) : "r"(a) : "memory");
  return v;
}
__device__ __forceinline__ uint4 ldg128(const void* a) {
  uint4 v;
  asm volatile("ld.global.nc.v4.u32 {%0, %1, %2, %3}, [%4];" : "=r"(v.x), "=r"(v.y), "=r"(v.z), "=r"(v.w) : "l"(a) : "memory");
  return v;
}
__device__ __forceinline__ uint2 ldg64(const void* a) {
  uint2 v;
  asm volatile("ld.global.nc.v2.u32 {%0, %1}, [%2];" : "=r"(v.x), "=r"(v.y) : "l"(a) : "memory");
  return v;
}
__device__ __forceinline__ void ldsm4(uint32_t* r, uint32_t a) {
  asm volatile("ldmatrix.sync.aligned.m8n8.x4.shared.b16 {%0, %1, %2, %3}, [%4];"
               : "=r"(r[0]), "=r"(r[1]), "=r"(r[2]), "=r"(r[3]) : "r"(a) : "memory");
}
__device__ __forceinline__ void ldsm4t(uint32_t* r, uint32_t a) {
  asm volatile("ldmatrix.sync.aligned.m8n8.x4.trans.shared.b16 {%0, %1, %2, %3}, [%4];"
               : "=r"(r[0]), "=r"(r[1]), "=r"(r[2]), "=r"(r[3]) : "r"(a) : "memory");
}
__device__ __forceinline__ uint4 lds128(uint32_t a) {
  uint4 v;
  asm volatile("ld.shared.v4.u32 {%0, %1, %2, %3}, [%4];" : "=r"(v.x), "=r"(v.y), "=r"(v.z), "=r"(v.w) : "r"(a) : "memory");
  return v;
}
__device__ __forceinline__ void sts128(uint32_t a, uint32_t x, uint32_t y, uint32_t z, uint32_t w) {
  asm volatile("st.shared.v4.u32 [%0], {%1, %2, %3, %4};" ::"r"(a), "r"(x), "r"(y), "r"(z), "r"(w) : "memory");
}
__device__ __forceinline__ void stsm4(uint32_t a, const uint32_t* r) {
  asm volatile("stmatrix.sync.aligned.m8n8.x4.shared.b16 [%0], {%1, %2, %3, %4};" ::"r"(a), "r"(r[0]), "r"(r[1]), "r"(r[2]), "r"(r[3]) : "memory");
}
__device__ __forceinline__ void stsm4t(uint32_t a, const uint32_t* r) {
  asm volatile("stmatrix.sync.aligned.m8n8.x4.trans.shared.b16 [%0], {%1, %2, %3, %4};" ::"r"(a), "r"(r[0]), "r"(r[1]), "r"(r[2]), "r"(r[3]) : "memory");
}
__device__ __forceinline__ uint32_t pack2(float lo, float hi) {
  uint32_t r;
  asm("cvt.rn.bf16x2.f32 %0, %1, %2;" : "=r"(r) : "f"(hi), "f"(lo));
  return r;
}
__device__ __forceinline__ uint32_t movm(uint32_t a) {
  uint32_t d;
  asm volatile("movmatrix.sync.aligned.m8n8.trans.b16 %0, %1;" : "=r"(d) : "r"(a));
  return d;
}
__device__ __forceinline__ uint32_t bmul(uint32_t a, uint32_t b) {
  uint32_t d;
  asm("mul.rn.bf16x2 %0, %1, %2;" : "=r"(d) : "r"(a), "r"(b));
  return d;
}
__device__ __forceinline__ uint32_t badd(uint32_t a, uint32_t b) {
  uint32_t d;
  asm("add.rn.bf16x2 %0, %1, %2;" : "=r"(d) : "r"(a), "r"(b));
  return d;
}
__device__ __forceinline__ float bf_lo(uint32_t x) { return __uint_as_float(x << 16); }
__device__ __forceinline__ float bf_hi(uint32_t x) { return __uint_as_float(x & 0xFFFF0000u); }
__device__ __forceinline__ float ex2(float x) {
  float y;
  asm("ex2.approx.ftz.f32 %0, %1;" : "=f"(y) : "f"(x));
  return y;
}
__device__ __forceinline__ float rcp(float x) {
  float y;
  asm("rcp.approx.ftz.f32 %0, %1;" : "=f"(y) : "f"(x));
  return y;
}
__device__ __forceinline__ void mma16816(float* d, uint32_t a0, uint32_t a1, uint32_t a2, uint32_t a3, uint32_t b0, uint32_t b1) {
  asm volatile("mma.sync.aligned.m16n8k16.row.col.f32.bf16.bf16.f32 {%0, %1, %2, %3}, {%4, %5, %6, %7}, {%8, %9}, {%0, %1, %2, %3};"
               : "+f"(d[0]), "+f"(d[1]), "+f"(d[2]), "+f"(d[3])
               : "r"(a0), "r"(a1), "r"(a2), "r"(a3), "r"(b0), "r"(b1));
}
__device__ __forceinline__ void mma1688(float* d, uint32_t a0, uint32_t a1, uint32_t b0) {
  asm volatile("mma.sync.aligned.m16n8k8.row.col.f32.bf16.bf16.f32 {%0, %1, %2, %3}, {%4, %5}, {%6}, {%0, %1, %2, %3};"
               : "+f"(d[0]), "+f"(d[1]), "+f"(d[2]), "+f"(d[3])
               : "r"(a0), "r"(a1), "r"(b0));
}

template <int N> struct WgRS;
template <int N> struct WgSST;
template <> struct WgRS<32> {
  template <uint32_t HB>
  static __device__ __forceinline__ void mma(float* d, const uint32_t* a, uint32_t db) {
    asm volatile("{\n.reg .pred p;\n.reg .b64 db;\nsetp.ne.b32 p, %22, 0;\n"
      "mov.b64 db, {%20, %21};\n"
      "wgmma.mma_async.sync.aligned.m64n32k16.f32.bf16.bf16 {"
      "%0, %1, %2, %3, %4, %5, %6, %7, %8, %9, %10, %11, %12, %13, %14, %15"
      "}, {%16, %17, %18, %19}, db, p, 1, 1, 1;\n}\n"
      : "+f"(d[0]), "+f"(d[1]), "+f"(d[2]), "+f"(d[3]), "+f"(d[4]), "+f"(d[5]), "+f"(d[6]), "+f"(d[7]),
        "+f"(d[8]), "+f"(d[9]), "+f"(d[10]), "+f"(d[11]), "+f"(d[12]), "+f"(d[13]), "+f"(d[14]), "+f"(d[15])
      : "r"(a[0]), "r"(a[1]), "r"(a[2]), "r"(a[3]), "r"(db), "n"(HB), "n"(1));
  }
  template <uint32_t HB>
  static __device__ __forceinline__ void set(float* d, const uint32_t* a, uint32_t db) {
    asm volatile("{\n.reg .pred p;\n.reg .b64 db;\nsetp.ne.b32 p, %22, 0;\n"
      "mov.b64 db, {%20, %21};\n"
      "wgmma.mma_async.sync.aligned.m64n32k16.f32.bf16.bf16 {"
      "%0, %1, %2, %3, %4, %5, %6, %7, %8, %9, %10, %11, %12, %13, %14, %15"
      "}, {%16, %17, %18, %19}, db, p, 1, 1, 1;\n}\n"
      : "=f"(d[0]), "=f"(d[1]), "=f"(d[2]), "=f"(d[3]), "=f"(d[4]), "=f"(d[5]), "=f"(d[6]), "=f"(d[7]),
        "=f"(d[8]), "=f"(d[9]), "=f"(d[10]), "=f"(d[11]), "=f"(d[12]), "=f"(d[13]), "=f"(d[14]), "=f"(d[15])
      : "r"(a[0]), "r"(a[1]), "r"(a[2]), "r"(a[3]), "r"(db), "n"(HB), "n"(0));
  }
};
template <> struct WgRS<64> {
  template <uint32_t HB>
  static __device__ __forceinline__ void mma(float* d, const uint32_t* a, uint32_t db) {
    asm volatile("{\n.reg .pred p;\n.reg .b64 db;\nsetp.ne.b32 p, %38, 0;\n"
      "mov.b64 db, {%36, %37};\n"
      "wgmma.mma_async.sync.aligned.m64n64k16.f32.bf16.bf16 {"
      "%0, %1, %2, %3, %4, %5, %6, %7, %8, %9, %10, %11, %12, %13, %14, %15, "
      "%16, %17, %18, %19, %20, %21, %22, %23, %24, %25, %26, %27, %28, %29, %30, %31"
      "}, {%32, %33, %34, %35}, db, p, 1, 1, 1;\n}\n"
      : "+f"(d[0]), "+f"(d[1]), "+f"(d[2]), "+f"(d[3]), "+f"(d[4]), "+f"(d[5]), "+f"(d[6]), "+f"(d[7]),
        "+f"(d[8]), "+f"(d[9]), "+f"(d[10]), "+f"(d[11]), "+f"(d[12]), "+f"(d[13]), "+f"(d[14]), "+f"(d[15]),
        "+f"(d[16]), "+f"(d[17]), "+f"(d[18]), "+f"(d[19]), "+f"(d[20]), "+f"(d[21]), "+f"(d[22]), "+f"(d[23]),
        "+f"(d[24]), "+f"(d[25]), "+f"(d[26]), "+f"(d[27]), "+f"(d[28]), "+f"(d[29]), "+f"(d[30]), "+f"(d[31])
      : "r"(a[0]), "r"(a[1]), "r"(a[2]), "r"(a[3]), "r"(db), "n"(HB), "n"(1));
  }
  template <uint32_t HB>
  static __device__ __forceinline__ void set(float* d, const uint32_t* a, uint32_t db) {
    asm volatile("{\n.reg .pred p;\n.reg .b64 db;\nsetp.ne.b32 p, %38, 0;\n"
      "mov.b64 db, {%36, %37};\n"
      "wgmma.mma_async.sync.aligned.m64n64k16.f32.bf16.bf16 {"
      "%0, %1, %2, %3, %4, %5, %6, %7, %8, %9, %10, %11, %12, %13, %14, %15, "
      "%16, %17, %18, %19, %20, %21, %22, %23, %24, %25, %26, %27, %28, %29, %30, %31"
      "}, {%32, %33, %34, %35}, db, p, 1, 1, 1;\n}\n"
      : "=f"(d[0]), "=f"(d[1]), "=f"(d[2]), "=f"(d[3]), "=f"(d[4]), "=f"(d[5]), "=f"(d[6]), "=f"(d[7]),
        "=f"(d[8]), "=f"(d[9]), "=f"(d[10]), "=f"(d[11]), "=f"(d[12]), "=f"(d[13]), "=f"(d[14]), "=f"(d[15]),
        "=f"(d[16]), "=f"(d[17]), "=f"(d[18]), "=f"(d[19]), "=f"(d[20]), "=f"(d[21]), "=f"(d[22]), "=f"(d[23]),
        "=f"(d[24]), "=f"(d[25]), "=f"(d[26]), "=f"(d[27]), "=f"(d[28]), "=f"(d[29]), "=f"(d[30]), "=f"(d[31])
      : "r"(a[0]), "r"(a[1]), "r"(a[2]), "r"(a[3]), "r"(db), "n"(HB), "n"(0));
  }
};
template <> struct WgSST<48> {
  template <uint32_t HA, uint32_t HB>
  static __device__ __forceinline__ void mma(float* d, uint32_t da, uint32_t db, int sc) {
    asm volatile("{\n.reg .pred p;\n.reg .b64 da, db;\nsetp.ne.b32 p, %28, 0;\n"
      "mov.b64 da, {%24, %25};\nmov.b64 db, {%26, %27};\n"
      "wgmma.mma_async.sync.aligned.m64n48k16.f32.bf16.bf16 {"
      "%0, %1, %2, %3, %4, %5, %6, %7, %8, %9, %10, %11, %12, %13, %14, %15, "
      "%16, %17, %18, %19, %20, %21, %22, %23"
      "}, da, db, p, 1, 1, 0, 1;\n}\n"
      : "+f"(d[0]), "+f"(d[1]), "+f"(d[2]), "+f"(d[3]), "+f"(d[4]), "+f"(d[5]), "+f"(d[6]), "+f"(d[7]),
        "+f"(d[8]), "+f"(d[9]), "+f"(d[10]), "+f"(d[11]), "+f"(d[12]), "+f"(d[13]), "+f"(d[14]), "+f"(d[15]),
        "+f"(d[16]), "+f"(d[17]), "+f"(d[18]), "+f"(d[19]), "+f"(d[20]), "+f"(d[21]), "+f"(d[22]), "+f"(d[23])
      : "r"(da), "n"(HA), "r"(db), "n"(HB), "r"(sc));
  }
};
template <> struct WgSST<80> {
  template <uint32_t HA, uint32_t HB>
  static __device__ __forceinline__ void mma(float* d, uint32_t da, uint32_t db, int sc) {
    asm volatile("{\n.reg .pred p;\n.reg .b64 da, db;\nsetp.ne.b32 p, %44, 0;\n"
      "mov.b64 da, {%40, %41};\nmov.b64 db, {%42, %43};\n"
      "wgmma.mma_async.sync.aligned.m64n80k16.f32.bf16.bf16 {"
      "%0, %1, %2, %3, %4, %5, %6, %7, %8, %9, %10, %11, %12, %13, %14, %15, "
      "%16, %17, %18, %19, %20, %21, %22, %23, %24, %25, %26, %27, %28, %29, %30, %31, "
      "%32, %33, %34, %35, %36, %37, %38, %39"
      "}, da, db, p, 1, 1, 0, 1;\n}\n"
      : "+f"(d[0]), "+f"(d[1]), "+f"(d[2]), "+f"(d[3]), "+f"(d[4]), "+f"(d[5]), "+f"(d[6]), "+f"(d[7]),
        "+f"(d[8]), "+f"(d[9]), "+f"(d[10]), "+f"(d[11]), "+f"(d[12]), "+f"(d[13]), "+f"(d[14]), "+f"(d[15]),
        "+f"(d[16]), "+f"(d[17]), "+f"(d[18]), "+f"(d[19]), "+f"(d[20]), "+f"(d[21]), "+f"(d[22]), "+f"(d[23]),
        "+f"(d[24]), "+f"(d[25]), "+f"(d[26]), "+f"(d[27]), "+f"(d[28]), "+f"(d[29]), "+f"(d[30]), "+f"(d[31]),
        "+f"(d[32]), "+f"(d[33]), "+f"(d[34]), "+f"(d[35]), "+f"(d[36]), "+f"(d[37]), "+f"(d[38]), "+f"(d[39])
      : "r"(da), "n"(HA), "r"(db), "n"(HB), "r"(sc));
  }
};
template <> struct WgSST<192> {
  template <uint32_t HA, uint32_t HB>
  static __device__ __forceinline__ void mma(float* d, uint32_t da, uint32_t db, int sc) {
    asm volatile("{\n.reg .pred p;\n.reg .b64 da, db;\nsetp.ne.b32 p, %100, 0;\n"
      "mov.b64 da, {%96, %97};\nmov.b64 db, {%98, %99};\n"
      "wgmma.mma_async.sync.aligned.m64n192k16.f32.bf16.bf16 {"
      "%0, %1, %2, %3, %4, %5, %6, %7, %8, %9, %10, %11, %12, %13, %14, %15, "
      "%16, %17, %18, %19, %20, %21, %22, %23, %24, %25, %26, %27, %28, %29, %30, %31, "
      "%32, %33, %34, %35, %36, %37, %38, %39, %40, %41, %42, %43, %44, %45, %46, %47, "
      "%48, %49, %50, %51, %52, %53, %54, %55, %56, %57, %58, %59, %60, %61, %62, %63, "
      "%64, %65, %66, %67, %68, %69, %70, %71, %72, %73, %74, %75, %76, %77, %78, %79, "
      "%80, %81, %82, %83, %84, %85, %86, %87, %88, %89, %90, %91, %92, %93, %94, %95"
      "}, da, db, p, 1, 1, 0, 1;\n}\n"
      : "+f"(d[0]), "+f"(d[1]), "+f"(d[2]), "+f"(d[3]), "+f"(d[4]), "+f"(d[5]), "+f"(d[6]), "+f"(d[7]),
        "+f"(d[8]), "+f"(d[9]), "+f"(d[10]), "+f"(d[11]), "+f"(d[12]), "+f"(d[13]), "+f"(d[14]), "+f"(d[15]),
        "+f"(d[16]), "+f"(d[17]), "+f"(d[18]), "+f"(d[19]), "+f"(d[20]), "+f"(d[21]), "+f"(d[22]), "+f"(d[23]),
        "+f"(d[24]), "+f"(d[25]), "+f"(d[26]), "+f"(d[27]), "+f"(d[28]), "+f"(d[29]), "+f"(d[30]), "+f"(d[31]),
        "+f"(d[32]), "+f"(d[33]), "+f"(d[34]), "+f"(d[35]), "+f"(d[36]), "+f"(d[37]), "+f"(d[38]), "+f"(d[39]),
        "+f"(d[40]), "+f"(d[41]), "+f"(d[42]), "+f"(d[43]), "+f"(d[44]), "+f"(d[45]), "+f"(d[46]), "+f"(d[47]),
        "+f"(d[48]), "+f"(d[49]), "+f"(d[50]), "+f"(d[51]), "+f"(d[52]), "+f"(d[53]), "+f"(d[54]), "+f"(d[55]),
        "+f"(d[56]), "+f"(d[57]), "+f"(d[58]), "+f"(d[59]), "+f"(d[60]), "+f"(d[61]), "+f"(d[62]), "+f"(d[63]),
        "+f"(d[64]), "+f"(d[65]), "+f"(d[66]), "+f"(d[67]), "+f"(d[68]), "+f"(d[69]), "+f"(d[70]), "+f"(d[71]),
        "+f"(d[72]), "+f"(d[73]), "+f"(d[74]), "+f"(d[75]), "+f"(d[76]), "+f"(d[77]), "+f"(d[78]), "+f"(d[79]),
        "+f"(d[80]), "+f"(d[81]), "+f"(d[82]), "+f"(d[83]), "+f"(d[84]), "+f"(d[85]), "+f"(d[86]), "+f"(d[87]),
        "+f"(d[88]), "+f"(d[89]), "+f"(d[90]), "+f"(d[91]), "+f"(d[92]), "+f"(d[93]), "+f"(d[94]), "+f"(d[95])
      : "r"(da), "n"(HA), "r"(db), "n"(HB), "r"(sc));
  }
};

struct FftConst {
  uint32_t f[2][4], fi[4][4];
  float ta[4], tb[4];
};
__device__ __forceinline__ void cis(int m, float scale, float& c, float& s) {
  const float a = (float)m * (-6.283185307179586f * scale);
  c = __cosf(a);
  s = __sinf(a);
}
__device__ __forceinline__ void fft_tables(uint32_t (&v)[12], int tw) {
  const int row = tw >> 2, ch = tw & 3;
#pragma unroll
  for (int i = 0; i < 4; i++) {
    float c[2], s[2], x[2];
#pragma unroll
    for (int e = 0; e < 2; e++) {
      cis((((32 * (8 * ch + 2 * i + e) + 15) * (4 * row - 63) + 2048) & 4095) - 2048, 1.f / 4096, c[e], s[e]);
      float gc, gs;
      cis((((row & 15) * (8 * (ch & 1) + 2 * i + e) + 8) & 15) - 8, 1.f / 16, gc, gs);
      x[e] = (row >> 4) == (ch >> 1) ? gc : (ch >> 1) ? gs : -gs;
    }
    v[i] = pack2(c[0] * 0.125f, c[1] * 0.125f);
    v[4 + i] = pack2(s[0] * 0.125f, s[1] * 0.125f);
    v[8 + i] = pack2(x[0], x[1]);
  }
#pragma unroll
  for (int i = 0; i < 12; i++) asm volatile("" : "+r"(v[i]));
}
__device__ __forceinline__ void fft_tables_store(const uint32_t (&v)[12], uint32_t sb, int tw) {
  const int row = tw >> 2;
  const uint32_t x = ((tw ^ (row >> 1)) & 3) << 4, a = sb + OFF_FT + (16 * (row >> 3) + (row & 7)) * 64 + x;
  sts128(a, v[0], v[1], v[2], v[3]);
  sts128(a + 512, v[4], v[5], v[6], v[7]);
  sts128(sb + OFF_GT + row * 64 + x, v[8], v[9], v[10], v[11]);
}
__device__ __forceinline__ void fft_twiddles(float (&v)[4], int tw) {
#pragma unroll
  for (int i = 0; i < 2; i++) {
    float c, s;
    cis((2 * (2 * (tw & 3) + i) - 15) * (4 * (tw >> 2) - 63), 1.f / 4096, c, s);
    v[2 * i] = __fdividef(-s, 1.f + c);
    v[2 * i + 1] = s;
  }
  pin<4>(v);
}
__device__ __forceinline__ void fft_matrices(FftConst& k, uint32_t sb, int w, int lane) {
  const uint32_t x = (lane >> 1) & 3;
  const uint4 t0 = lds128(sb + OFF_TT + 512 * w + 16 * lane), t1 = lds128(sb + OFF_TT + 512 * w + 16 * (lane ^ 3));
  k.ta[0] = __uint_as_float(t0.x); k.tb[0] = __uint_as_float(t0.y); k.ta[1] = __uint_as_float(t0.z); k.tb[1] = __uint_as_float(t0.w);
  k.ta[3] = __uint_as_float(t1.x); k.tb[3] = __uint_as_float(t1.y); k.ta[2] = __uint_as_float(t1.z); k.tb[2] = __uint_as_float(t1.w);
#pragma unroll
  for (int i = 0; i < 2; i++) {
    ldsm4(k.f[i], sb + OFF_FT + (16 * w + (lane & 15)) * 64 + (((2 * i + (lane >> 4)) ^ x) << 4));
    ldsm4t(k.fi[i], sb + OFF_FT + (32 * i + lane) * 64 + ((w ^ x) << 4));
#pragma unroll
    for (int j = 0; j < 4; j++) {
      k.fi[2 + i][j] = (j & 1) ? k.fi[i][j - 1] ^ 0x80008000u : k.fi[i][j + 1];
      asm volatile("" : "+r"(k.fi[2 + i][j]));
    }
  }
}
__device__ __forceinline__ void rot(bool inv, float& x, float& y, float a, float b) {
  x = fmaf(inv ? -a : a, y, x);
  y = fmaf(inv ? -b : b, x, y);
  x = fmaf(inv ? -a : a, y, x);
}
__device__ __forceinline__ void twiddle_fwd(uint32_t (&a)[4][4], float* d, const FftConst& k) {
#pragma unroll
  for (int q = 0; q < 4; q++)
#pragma unroll
    for (int j = 0; j < 2; j++) {
      float* x = d + 8 * q + 4 * j;
      rot(j, x[0], x[2], k.ta[2 * j], k.tb[2 * j]);
      rot(j, x[1], x[3], k.ta[2 * j + 1], k.tb[2 * j + 1]);
      a[q & 2][2 * j + (q & 1)] = pack2(x[0], x[1]);
      a[(q & 2) + 1][2 * j + (q & 1)] = pack2(x[2], x[3]);
    }
}
__device__ __forceinline__ void g_step(float* d, const uint32_t (&a)[4][4], uint32_t dre, uint32_t dim) {
  WgRS<32>::set<HI_SW64>(d, a[0], dre);
  WgRS<32>::set<HI_SW64>(d + 16, a[2], dre);
  WgRS<32>::mma<HI_SW64>(d, a[1], dim);
  WgRS<32>::mma<HI_SW64>(d + 16, a[3], dim);
  wg_commit();
}

__device__ __forceinline__ void conv_channel(const FftConst& k, uint32_t sb, int c, int wg, int w, int lane) {
  const uint32_t cb = sb + off_ch(c), bars = sb + OFF_BAR;
  const uint32_t du = desc_lo(cb, 1024), dg = desc_lo(sb + OFF_GT, 16), dz = desc_lo(cb + U_BYTES, 16);
  float U[32], H[32];
  uint32_t a[4][4], e[4][4];
  const float dv = __uint_as_float(lds32(sb + OFF_D + 4 * c));
  wg_fence();
  WgRS<64>::set<HI_SW32>(H, k.f[0], du + 256);
  WgRS<64>::mma<HI_SW32>(H, k.f[1], du + 256 + 32);
  wg_commit();
  wg_wait<0>();
  pin<32>(H);
  TSM(w == 0 && c == 1, 114);
  twiddle_fwd(a, H, k);
  asm volatile("" : "+r"(a[0][0]), "+r"(a[1][1]), "+r"(a[2][2]), "+r"(a[3][3]));
  TSM(w == 0 && c == 1, 127);
  if (ATT_GATE && H_EARLY) mbar_wait(bars + 8 * B_ATTN, 0);
  mbar_wait(bars + 8 * (B_U + (c < 3 ? c : 3)), 0);
  TSM(w == 0 && c < 3, 7 + wg);
  wg_fence();
  WgRS<64>::set<HI_SW32>(U, k.f[0], du);
  WgRS<64>::mma<HI_SW32>(U, k.f[1], du + 32);
  wg_commit();
  g_step(H, a, dg, dg + 64);
  wg_wait<1>();
  pin<32>(U);
  twiddle_fwd(e, U, k);
  wg_fence();
  g_step(U, e, dg, dg + 64);
  wg_wait<0>();
  pin<32>(U);
  pin<32>(H);
#pragma unroll
  for (int j = 0; j < 2; j++) {
    float pr[4][2], pi[4][2];
#pragma unroll
    for (int x = 0; x < 2; x++) {
      H[4 * j + x] += dv;
#pragma unroll
      for (int m = 0; m < 4; m++) {
#pragma unroll
        for (int q = 0; q <= m; q++) {
          const int ih = 16 * (q >> 1) + 2 * (q & 1) + 4 * j + x, iu = 16 * ((m - q) >> 1) + 2 * ((m - q) & 1) + 4 * j + x;
          pr[m][x] = q ? fmaf(H[ih], U[iu], pr[m][x]) : H[ih] * U[iu];
          pi[m][x] = q ? fmaf(H[ih], U[iu + 8], pi[m][x]) : H[ih] * U[iu + 8];
          pr[m][x] = fmaf(-H[ih + 8], U[iu + 8], pr[m][x]);
          pi[m][x] = fmaf(H[ih + 8], U[iu], pi[m][x]);
        }
      }
    }
#pragma unroll
    for (int m = 0; m < 4; m++) {
      a[m & 2][2 * j + (m & 1)] = pack2(pr[m][0], pr[m][1]);
      a[(m & 2) + 1][2 * j + (m & 1)] = pack2(pi[m][0], pi[m][1]);
    }
  }
  wg_fence();
  g_step(U, a, dg + 64, dg);
  const uint32_t za = cb + U_BYTES + (8 * w + (lane & 7)) * 128 + (((lane >> 3) ^ (lane & 7)) << 4);
  const uint32_t ya = cb + (lane >> 4) * 1024 + (8 * w + (lane & 7)) * 32 + ((((lane >> 3) ^ (lane >> 2)) & 1) << 4);
  wg_sync(1 + wg);
  wg_wait<0>();
  pin<32>(U);
  TSIF(w == 0, 80 + c);
#pragma unroll
  for (int p = 0; p < 2; p++) {
#pragma unroll
    for (int i = 0; i < 4; i++) {
      const int j = i & 1;
      float* x = U + 16 * p + 4 * j + (i & 2);
      rot(!j, x[8], x[0], k.ta[2 * j], k.tb[2 * j]);
      rot(!j, x[9], x[1], k.ta[2 * j + 1], k.tb[2 * j + 1]);
      e[p][i] = pack2(x[8], x[9]);
      e[2 + p][i] = pack2(x[0], x[1]);
    }
    stsm4(za ^ (64 * p), e[p]);
    stsm4((za ^ (64 * p)) + 4096, e[2 + p]);
  }
  fence_async_smem();
  wg_sync(1 + wg);
  wg_fence();
  WgRS<64>::set<HI_SW128>(H, k.fi[0], dz);
#pragma unroll
  for (int ks = 1; ks < 4; ks++) WgRS<64>::mma<HI_SW128>(H, k.fi[ks], dz + 128 * ks);
  wg_commit();
  wg_wait<0>();
  pin<32>(H);
  TSIF(w == 0, 88 + c);
#pragma unroll
  for (int j = 0; j < 8; j++)
    a[j >> 2][j & 3] = j < 2 ? pack2(H[4 * j], H[4 * j + 1]) : pack2(H[4 * j] + H[4 * j - 6], H[4 * j + 1] + H[4 * j - 5]);
  stsm4(ya, a[0]);
  stsm4(ya + 2048, a[1]);
  fence_async_smem();
  __syncwarp();
}

__device__ __forceinline__ void prep_slab(uint4* res, const uint2* sw, uint32_t sb, int slab, int w, int lane) {
  const int t = lane & 3, tp = (lane & 7) >> 1, pos = 8 * tp + 2 * (((lane >> 3) + tp) & 3) + (lane & 1);
  const uint32_t base = sb + OFF_KVS + slab * KVS_BYTES + pos * 128;
  uint32_t kk[2][4][4], vv[2][4];
  mbar_wait(sb + OFF_BAR + 8 * (B_KV + slab), 0);
#pragma unroll
  for (int h = 0; h < 2; h++) {
#pragma unroll
    for (int j = 0; j < 4; j++) {
      const uint32_t a = base + 128 * j;
      ldsm4t(kk[h][j], a + (((w + 4 * h) ^ ((a >> 7) & 7)) << 4));
    }
    const uint32_t a = base + KVS_V;
    ldsm4t(vv[h], a + (((w + 4 * h) ^ ((a >> 7) & 7)) << 4));
  }
#pragma unroll
  for (int h = 0; h < 2; h++) {
    uint32_t (&k)[4][4] = kk[h];
    uint32_t (&v)[4] = vv[h];
    const uint32_t w0 = __byte_perm(sw[h].x, 0, 0x1010), w1 = __byte_perm(sw[h].x, 0, 0x3232);
    const uint32_t w2 = __byte_perm(sw[h].y, 0, 0x1010), w3 = __byte_perm(sw[h].y, 0, 0x3232);
#pragma unroll
    for (int m = 0; m < 4; m++)
      v[m] = bmul(badd(badd(badd(bmul(k[0][m], w3), bmul(k[1][m], w2)), bmul(k[2][m], w1)), bmul(k[3][m], w0)), v[m]);
    uint32_t a[4];
#pragma unroll
    for (int m = 0; m < 4; m++) a[m] = (t & 1) ? v[(m + 3) & 3] : v[m];
    res[h] = (t & 2) ? make_uint4(a[2], a[3], a[0], a[1]) : make_uint4(a[0], a[1], a[2], a[3]);
  }
}

__device__ __forceinline__ void prep_gate(const Params& p, int b, int w, int lane) {
  uint2 gw[5], x[4][5];
#pragma unroll
  for (int j = 0; j < 5; j++) gw[j] = ldg64(reinterpret_cast<const uint2*>(p.gate_w) + lane + 32 * j);
#pragma unroll
  for (int i = 0; i < 4; i++)
#pragma unroll
    for (int j = 0; j < 5; j++)
      x[i][j] = ldg64(reinterpret_cast<const uint2*>(p.q) + (16 * b + 4 * w + i) * (DIM / 4) + lane + 32 * j);
  float s[4];
#pragma unroll
  for (int i = 0; i < 4; i++) {
    s[i] = 0.f;
#pragma unroll
    for (int j = 0; j < 5; j++) {
      const uint32_t m0 = bmul(x[i][j].x, gw[j].x), m1 = bmul(x[i][j].y, gw[j].y);
      s[i] += (bf_lo(m0) + bf_hi(m0)) + (bf_lo(m1) + bf_hi(m1));
    }
  }
  const bool h = lane & 16, q = lane & 8;
  const float a = (h ? s[2] : s[0]) + __shfl_xor_sync(0xffffffffu, h ? s[0] : s[2], 16);
  const float c = (h ? s[3] : s[1]) + __shfl_xor_sync(0xffffffffu, h ? s[1] : s[3], 16);
  float z = (q ? c : a) + __shfl_xor_sync(0xffffffffu, q ? a : c, 8);
#pragma unroll
  for (int o = 4; o > 0; o >>= 1) z += __shfl_xor_sync(0xffffffffu, z, o);
  z = bf_lo(pack2(z, 0.f));
  if ((lane & 7) == 0) g_gate[16 * b + 4 * w + (lane >> 3)] = bf_lo(pack2(__fdividef(1.f, 1.f + __expf(-z)), 0.f));
}

__device__ __forceinline__ uint32_t bmax(uint32_t a, uint32_t b) {
  uint32_t d;
  asm("max.bf16x2 %0, %1, %2;" : "=r"(d) : "r"(a), "r"(b));
  return d;
}
__device__ __forceinline__ void softmax_two(const float (&l)[2][2], uint32_t& p0, uint32_t& p1) {
  constexpr float kScale = 0.22360679774997896f, kLog2e = 1.4426950408889634f;
  const uint32_t r0 = pack2(l[0][0], l[1][0]), r1 = pack2(l[0][1], l[1][1]);
  const uint32_t x0 = pack2(bf_lo(r0) * kScale, bf_hi(r0) * kScale), x1 = pack2(bf_lo(r1) * kScale, bf_hi(r1) * kScale);
  uint32_t m = bmax(x0, x1);
  m = bmax(m, __shfl_xor_sync(0xffffffffu, m, 1));
  m = bmax(m, __shfl_xor_sync(0xffffffffu, m, 2));
  const float m0 = bf_lo(m) * kLog2e, m1 = bf_hi(m) * kLog2e;
  p0 = pack2(ex2(bf_lo(x0) * kLog2e - m0), ex2(bf_lo(x1) * kLog2e - m0));
  p1 = pack2(ex2(bf_hi(x0) * kLog2e - m1), ex2(bf_hi(x1) * kLog2e - m1));
}

__device__ __forceinline__ void halo_read(uint32_t (&kpv)[10], uint32_t (&vpv)[10], uint32_t (&tg)[7], const uint4* hp) {
#pragma unroll
  for (int j = 0; j < 7; j++) {
    uint32_t x0, x1, x2;
    asm volatile("ld.relaxed.gpu.global.v4.u32 {%0, %1, %2, %3}, [%4];"
                 : "=r"(x0), "=r"(x1), "=r"(x2), "=r"(tg[j]) : "l"(hp + 32 * j) : "memory");
    if (j < 4) kpv[3 * j] = x0; else vpv[3 * j - 10] = x0;
    if (j < 3) kpv[3 * j + 1] = x1; else vpv[3 * j - 9] = x1;
    if (j < 3) kpv[3 * j + 2] = x2; else if (j < 6) vpv[3 * j - 8] = x2;
  }
}

template <int ROT>
__device__ __forceinline__ void pack_qkv(const float* acc, uint32_t (&qlo)[10], uint32_t (&qhi)[10], uint32_t (&klo)[10],
                                         uint32_t (&khi)[10], uint32_t (&vlo)[10], uint32_t (&vhi)[10]) {
#pragma unroll
  for (int j = 0; j < 10; j++) {
    const int x = (j + ROT) % 10, tq = x < 8 ? x : 16 + x, tk = x < 8 ? 8 + x : 18 + x, tv = x < 8 ? 16 + x : 20 + x;
    khi[j] = pack2(acc[4 * tk + 2], acc[4 * tk + 3]);
    vhi[j] = movm(pack2(acc[4 * tv + 2], acc[4 * tv + 3]));
    qlo[j] = pack2(acc[4 * tq], acc[4 * tq + 1]);
    qhi[j] = pack2(acc[4 * tq + 2], acc[4 * tq + 3]);
    klo[j] = pack2(acc[4 * tk], acc[4 * tk + 1]);
    vlo[j] = pack2(acc[4 * tv], acc[4 * tv + 1]);
    asm volatile("" : "+r"(khi[j]), "+r"(qlo[j]), "+r"(qhi[j]), "+r"(klo[j]), "+r"(vlo[j]));
  }
}

template <int ROT> __device__ __forceinline__ void halo_send(const float* acc, uint4* ho, uint32_t tag) {
#pragma unroll
  for (int j = 0; j < 7; j++) {
    uint32_t x[3];
#pragma unroll
    for (int e = 0; e < 3; e++) {
      const int i = 3 * j + e, y = (i % 10 + ROT) % 10, tk = y < 8 ? 8 + y : 18 + y, tv = y < 8 ? 16 + y : 20 + y;
      x[e] = i < 10 ? pack2(acc[4 * tk + 2], acc[4 * tk + 3]) : i < 20 ? movm(pack2(acc[4 * tv + 2], acc[4 * tv + 3])) : 0u;
    }
    asm volatile("st.relaxed.gpu.global.v4.u32 [%0], {%1, %2, %3, %4};" ::"l"(ho + 32 * j), "r"(x[0]), "r"(x[1]), "r"(x[2]), "r"(tag) : "memory");
  }
}

__device__ __forceinline__ void attention(float* acc, uint32_t sb, int b, int par, int w, int lane, uint32_t tag) {
  const int g = lane >> 2, t = lane & 3;
  uint32_t klo[10], khi[10], vlo[10], vhi[10], qlo[10], qhi[10], kpv[10], vpv[10];
  if (HALO_FIRST && w == 3 && b < NCTA - 8) {
    uint4* ho = g_halo + (b * 2 + par) * 224 + lane;
    if (tail_first(b & 7)) halo_send<8>(acc, ho, tag);
    else halo_send<0>(acc, ho, tag);
    TSIF(par == 0, 76);
    pin<120>(acc);
  }
  if (tail_first(b & 7)) pack_qkv<8>(acc, qlo, qhi, klo, khi, vlo, vhi);
  else pack_qkv<0>(acc, qlo, qhi, klo, khi, vlo, vhi);
  const uint32_t xa = sb + OFF_KVX + (par * 3) * 2560 + lane * 16;
  if (w < 3) {
    sts128(xa + w * 2560, khi[0], khi[1], khi[2], khi[3]);
    sts128(xa + w * 2560 + 512, khi[4], khi[5], khi[6], khi[7]);
    sts128(xa + w * 2560 + 1024, khi[8], khi[9], vhi[0], vhi[1]);
    sts128(xa + w * 2560 + 1536, vhi[2], vhi[3], vhi[4], vhi[5]);
    sts128(xa + w * 2560 + 2048, vhi[6], vhi[7], vhi[8], vhi[9]);
  } else if (!HALO_FIRST && b < NCTA - 8) {
    uint4* ho = g_halo + (b * 2 + par) * 224 + lane;
#pragma unroll
    for (int j = 0; j < 7; j++) {
      const uint32_t x0 = j < 4 ? khi[3 * j] : vhi[3 * j - 10], x1 = j < 3 ? khi[3 * j + 1] : vhi[3 * j - 9];
      const uint32_t x2 = j < 3 ? khi[3 * j + 2] : j < 6 ? vhi[3 * j - 8] : 0u;
      asm volatile("st.relaxed.gpu.global.v4.u32 [%0], {%1, %2, %3, %4};" ::"l"(ho + 32 * j), "r"(x0), "r"(x1), "r"(x2), "r"(tag) : "memory");
    }
  }
  TSIF(par == 0 && w == 1, 64);
  TSIF(par == 0 && w == 3 && !HALO_FIRST, 76);
#pragma unroll
  for (int j = 0; j < 10; j++) vlo[j] = movm(vlo[j]);
  const bool far0 = 2 * t > g, far1 = 2 * t + 1 > g;
  const uint32_t mfar = (far0 ? 0x0000FFFFu : 0u) | (far1 ? 0xFFFF0000u : 0u);
  float slo[4][2], shi[4][2], lg[2][2];
  uint32_t phi[4], plo[4], qml[4], qmh[4];
#pragma unroll
  for (int h = 0; h < 4; h++) {
    const int f = h == 0 ? 0 : h == 1 ? 3 : h == 2 ? 5 : 8, hf = h < 2 ? 2 : 7;
    const bool mine = (h & 1) ? t >= 2 : t < 2;
    qml[h] = mine ? qlo[hf] : 0u;
    qmh[h] = mine ? qhi[hf] : 0u;
    float a[4] = {0.f, 0.f, 0.f, 0.f}, c[4] = {0.f, 0.f, 0.f, 0.f};
    mma16816(a, qlo[f], qhi[f], qlo[f + 1], qhi[f + 1], klo[f], klo[f + 1]);
    mma16816(c, qlo[f], qhi[f], qlo[f + 1], qhi[f + 1], khi[f], khi[f + 1]);
    mma1688(a, qml[h], qmh[h], klo[hf]);
    mma1688(c, qml[h], qmh[h], khi[hf]);
    slo[h][0] = a[0];
    slo[h][1] = a[1];
    shi[h][0] = lg[h & 1][0] = far0 ? a[2] : c[2];
    shi[h][1] = lg[h & 1][1] = far1 ? a[3] : c[3];
    if (!ATT_MERGE && (h & 1)) softmax_two(lg, phi[h - 1], phi[h]);
  }
  TSIF(par == 0 && w == 1, 65);
  wg_sync(1 + par);
  TSIF(par == 0 && w == 1, 66);
  const bool nohist = (w == 0) && (b < 8);
  const uint4* hp = g_halo + ((b - 8) * 2 + par) * 224 + lane;
  uint32_t tg[7];
  if (w > 0) {
    const uint4 v0 = lds128(xa + (w - 1) * 2560), v1 = lds128(xa + (w - 1) * 2560 + 512), v2 = lds128(xa + (w - 1) * 2560 + 1024);
    const uint4 v3 = lds128(xa + (w - 1) * 2560 + 1536), v4 = lds128(xa + (w - 1) * 2560 + 2048);
    kpv[0] = v0.x; kpv[1] = v0.y; kpv[2] = v0.z; kpv[3] = v0.w; kpv[4] = v1.x; kpv[5] = v1.y; kpv[6] = v1.z; kpv[7] = v1.w;
    kpv[8] = v2.x; kpv[9] = v2.y; vpv[0] = v2.z; vpv[1] = v2.w; vpv[2] = v3.x; vpv[3] = v3.y; vpv[4] = v3.z; vpv[5] = v3.w;
    vpv[6] = v4.x; vpv[7] = v4.y; vpv[8] = v4.z; vpv[9] = v4.w;
  } else if (nohist) {
#pragma unroll
    for (int j = 0; j < 10; j++) kpv[j] = vpv[j] = 0u;
  } else {
    TSIF(par == 0, 77);
    halo_read(kpv, vpv, tg, hp);
  }
  if (w == 0 && !nohist) {
    int spins = 0;
    while (true) {
      bool ok = true;
#pragma unroll
      for (int j = 0; j < 7; j++) ok = ok && tg[j] == tag;
      if (__all_sync(0xffffffffu, ok) || ++spins > SPIN_LIMIT) break;
      halo_read(kpv, vpv, tg, hp);
    }
    TSIF(par == 0, 79);
  }
#pragma unroll
  for (int h = 0; h < 4; h++) {
    const int f = h == 0 ? 0 : h == 1 ? 3 : h == 2 ? 5 : 8, hf = h < 2 ? 2 : 7;
    float a[4] = {0.f, 0.f, 0.f, 0.f};
    mma16816(a, qlo[f], qhi[f], qlo[f + 1], qhi[f + 1], kpv[f], kpv[f + 1]);
    mma1688(a, qml[h], qmh[h], kpv[hf]);
    const float ninf = __int_as_float(0xff800000);
    lg[h & 1][0] = far0 ? (nohist ? ninf : a[0]) : slo[h][0];
    lg[h & 1][1] = far1 ? (nohist ? ninf : a[1]) : slo[h][1];
    if (h & 1) {
      softmax_two(lg, plo[h - 1], plo[h]);
      if (ATT_MERGE) {
        const float lh[2][2] = {{shi[h - 1][0], shi[h - 1][1]}, {shi[h][0], shi[h][1]}};
        softmax_two(lh, phi[h - 1], phi[h]);
      }
    }
  }
  TSIF(par == 0 && w <= 1, 67 + w);
  uint32_t ov[20];
#pragma unroll
  for (int hp = 0; hp < 2; hp++) {
    const int hf = hp ? 7 : 2;
    float sh[4] = {0.f, 0.f, 0.f, 0.f}, i0 = 0.f, i1 = 0.f;
#pragma unroll
    for (int e = 0; e < 2; e++) {
      const int h = 2 * hp + e, f = h == 0 ? 0 : h == 1 ? 3 : h == 2 ? 5 : 8;
      const uint32_t a0 = plo[h] & mfar, a2 = plo[h] & ~mfar, a3 = phi[h] & mfar, c1 = phi[h] & ~mfar;
      float sum[4] = {0.f, 0.f, 0.f, 0.f};
      mma1688(sum, plo[h], phi[h], 0x3F803F80u);
      const float r0 = rcp(sum[0]), r1 = rcp(sum[2]);
#pragma unroll
      for (int j = f; j < f + 2; j++) {
        float o[4] = {0.f, 0.f, 0.f, 0.f};
        mma16816(o, a0, 0u, a2, a3, vpv[j], vlo[j]);
        mma1688(o, 0u, c1, vhi[j]);
        ov[2 * j] = pack2(o[0] * r0, o[1] * r0);
        ov[2 * j + 1] = pack2(o[2] * r1, o[3] * r1);
      }
      const bool mine = e ? g >= 4 : g < 4;
      mma16816(sh, a0, 0u, a2, a3, mine ? vpv[hf] : 0u, mine ? vlo[hf] : 0u);
      mma1688(sh, 0u, c1, mine ? vhi[hf] : 0u);
      if (e == 0 || t >= 2) {
        i0 = r0;
        i1 = r1;
      }
    }
    ov[2 * hf] = pack2(sh[0] * i0, sh[1] * i0);
    ov[2 * hf + 1] = pack2(sh[2] * i1, sh[3] * i1);
  }
  TS(32 + 4 * par + w);
  mbar_wait(sb + OFF_BAR + 8 * B_P1, 0);
  const uint32_t oa = sb + OFF_OA + (lane >> 4) * 2048 + (32 * w + 2 * (lane & 15) + par) * 16;
#pragma unroll
  for (int j = 0; j < 5; j++) stsm4(oa + 4096 * j, ov + 4 * j);
  TSIF(par == 0 && w == 0, 120);
  fence_async_smem();
  TSIF(par == 0 && w == 0, 121);
  __syncwarp();
  if (lane == 0) mbar_arrive(sb + OFF_BAR + 8 * B_ATTN);
  TSM(w == 0 || w == 2, 122 + par + (w == 2 ? 3 : 0));
}

struct Maps {
  CUtensorMap x, wm, wt, k, v, y, wo, qm, qt, om, ot, u;
};

__device__ __forceinline__ void load_stage(uint32_t sb, int kb, int b, const Maps& m) {
  const uint32_t st = sb + (kb & 3) * STAGE_BYTES, bar = sb + OFF_BAR + 8 * (B_FULL1 + (kb & 3));
  const int r = b >> 3, hg = b & 7, slab = kb - KV_KB;
  const bool kv = slab >= 0 && slab < 5;
  const uint32_t kbar = sb + OFF_BAR + 8 * (B_KV + slab), dst = sb + OFF_KVS + slab * KVS_BYTES;
  mbar_expect_tx(bar, STAGE_BYTES);
  if (kv) mbar_expect_tx(kbar, KVS_BYTES);
  tma_3d(st, &m.x, 64 * kb, 64 * r, 0, bar);
  if (kv && KV_MIX) tma_3d(dst, &m.k, 0, 32 * (b >> 1) - 3, 2 * slab + (b & 1), kbar);
  tma_3d(st + ST_W, &m.wm, 80 * hg + (tail_first(hg) ? 16 : 0), 64 * kb, 0, bar);
  if (kv && KV_MIX) tma_3d(dst + KVS_V, &m.v, 0, 32 * (b >> 1), 2 * slab + (b & 1), kbar);
  tma_3d(st + ST_WT, &m.wt, 80 * hg + (tail_first(hg) ? 0 : 64), 64 * kb, 0, bar);
  if (kv && !KV_MIX) tma_3d(dst, &m.k, 0, 32 * (b >> 1) - 3, 2 * slab + (b & 1), kbar);
  if (kv && !KV_MIX) tma_3d(dst + KVS_V, &m.v, 0, 32 * (b >> 1), 2 * slab + (b & 1), kbar);
}

__global__ void __launch_bounds__(NTHR, 1) fused_kernel(const __grid_constant__ Maps m, const Params p) {
  extern __shared__ __align__(1024) uint8_t smem[];
  const uint32_t sb = (uint32_t)__cvta_generic_to_shared(smem);
  const uint32_t bars = sb + OFF_BAR;
  const int tid = threadIdx.x, lane = tid & 31;
  int b = blockIdx.x;
  if (BMAP == 1) b = (((b & 63) >> 3) * 2 + (b & 1)) * 8 + (((b < 64 ? 0x6521 : 0x7430) >> (4 * ((b >> 1) & 3))) & 7);
  if (BMAP == 2) b = ((b & 63) >> 2) * 8 + (((b < 64 ? 0x6521 : 0x7430) >> (4 * (b & 3))) & 7);
  if (BMAP == 3) b = (((b & 63) >> 3) * 2 + (b & 1)) * 8 + (((b < 64 ? 0x7430 : 0x6521) >> (4 * ((b >> 1) & 3))) & 7);
  if (BMAP == 4) b = (((b >> 4) * 2 + (b & 1)) * 8) + ((b >> 1) & 7);
  if (BMAP == 5) b = 127 - b;
  const int r = b >> 3, hg = b & 7;

  if (tid == T_ISSUE) {
    TSM(true, 0);
#pragma unroll
    for (int i = 0; i < 4; i++) mbar_init(bars + 8 * (B_FULL1 + i), 1);
#pragma unroll
    for (int i = 0; i < 3; i++) mbar_init(bars + 8 * (B_KV + i), 1);
    fence_async_smem();
#pragma unroll 1
    for (int kb = 0; kb <= PRE2; kb++) load_stage(sb, kb, b, m);
  } else if (tid >= T_PF && tid < T_PF + 12) {
    tm_prefetch(&m.x + (tid - T_PF));
  } else if (tid == T_INIT) {
#pragma unroll
    for (int i = 0; i < 4; i++) mbar_init(bars + 8 * (B_EMPTY1 + i), 8);
#pragma unroll
    for (int i = 0; i < 8; i++) mbar_init(bars + 8 * (B_FULL2 + i), 1);
#pragma unroll
    for (int i = 0; i < 4; i++) mbar_init(bars + 8 * (B_EMPTY2 + i), 8);
#pragma unroll
    for (int i = 0; i < 4; i++) mbar_init(bars + 8 * (B_U + i), 1);
    mbar_init(bars + 8 * B_HA, 4);
    mbar_init(bars + 8 * B_GATE, 4);
    mbar_init(bars + 8 * B_HB, 1);
    mbar_init(bars + 8 * B_KVD, 4);
    mbar_init(bars + 8 * B_QF, 1);
    mbar_init(bars + 8 * B_ATTN, 8);
    mbar_init(bars + 8 * B_P1, 8);
    mbar_init(bars + 8 * B_C34, 1);
#pragma unroll
    for (int i = 0; i < 5; i++) mbar_init(bars + 8 * (B_YST + i), 4);
#pragma unroll
    for (int i = 0; i < 5; i++) mbar_init(bars + 8 * (B_US + i), 4);
    mbar_init(bars + 8 * B_YSIG, 1);
    mbar_init(bars + 8 * B_YFULL, 1);
    mbar_init(bars + 8 * B_EPOCH, 1);
    mbar_init(bars + 8 * B_PREP, 4);
    mbar_init(bars + 8 * B_USIG, 1);
    mbar_init(bars + 8 * B_WST, 1);
#pragma unroll
    for (int i = 3; i < 5; i++) mbar_init(bars + 8 * (B_KV + i), 1);
    mbar_init(bars + 8 * B_E3, 8);
    mbar_init(bars + 8 * B_LAST, 1);
    mbar_init(bars + 8 * B_OSIG, 1);
    mbar_init(bars + 8 * B_WOP, 1);
    fence_async_smem();
  }
  const int warp = __shfl_sync(0xffffffffu, tid >> 5, 0), wg = warp >> 2, w = warp & 3;
  __syncthreads();

  if (wg == 3) {
    asm volatile("setmaxnreg.dec.sync.aligned.u32 56;");
    if (w == 0) {
      if (lane == 0) {
#pragma unroll 1
        for (int kb = 1 + PRE2; kb < 10; kb++) {
          if (kb >= 4 && SLEEP_P1) mbar_sleep(bars + 8 * (kb == 7 ? B_E3 : B_EMPTY1 + (kb & 3)), (kb >> 3) & 1);
          if (kb >= 4 && !SLEEP_P1) mbar_wait(bars + 8 * (kb == 7 ? B_E3 : B_EMPTY1 + (kb & 3)), (kb >> 3) & 1);
          TSIF(kb >= 4, 44 + kb);
          load_stage(sb, kb, b, m);
          TSIF(kb == 3, 60);
          if (kb == TRIG_KB) mbar_arrive(bars + 8 * B_LAST);
        }
        mbar_sleep(bars + 8 * B_WOP, 0);
        mbar_sleep(bars + 8 * WL_TRIG, 0);
        mbar_sleep(bars + 8 * B_EPOCH, 0);
        flag_wait(g_cnt + C_W + 32 * hg, (lds32(sb + OFF_EPOCH) + 1) * 16);
        TS(30);
#pragma unroll 1
        for (int j = 0; j < 8; j++) {
          if (j >= 6) mbar_sleep(bars + 8 * (B_EMPTY2 + j - 6), 0);
          if (j == 4) mbar_sleep(bars + 8 * B_ATTN, 0);
          TSIF(j >= 6, 100 + j);
          if (RF_GATE && j == 6) mbar_sleep(bars + 8 * B_YSIG, 0);
          mbar_expect_tx(bars + 8 * (B_FULL2 + j), j == 0 ? WO_BYTES : j == 5 ? O_BYTES + WO_BYTES + 512 : O_BYTES + WO_BYTES);
          bulk_load(sb + off_w(j), g_WO + (hg * 8 + step_src(hg, j)) * 800, WO_BYTES, bars + 8 * (B_FULL2 + j));
        }
        mbar_sleep(bars + 8 * (B_EMPTY2 + 3), 0);
        mbar_expect_tx(bars + 8 * B_QF, O_BYTES);
        tma_2d(sb + OFF_QS, &m.qm, 80 * hg, 128 * r, bars + 8 * B_QF);
        tma_2d(sb + OFF_QT, &m.qt, 80 * hg + 64, 128 * r, bars + 8 * B_QF);
      }
    } else if (w == 1) {
      unsigned epoch = 0;
      if (lane == 0) {
        epoch = atomicAdd(g_cnt + C_LAUNCH, 1u) / NCTA;
        asm volatile("st.shared.u32 [%0], %1;" ::"r"(sb + OFF_EPOCH), "r"(epoch) : "memory");
        mbar_arrive(bars + 8 * B_EPOCH);
        mbar_sleep(bars + 8 * B_KVD, 0);
        mbar_expect_tx(bars + 8 * B_HB, 5 * 4096);
#pragma unroll 1
        for (int c = 0; c < 5; c++) {
          if (c == 3) mbar_sleep(bars + 8 * B_S3, 0);
          bulk_load(sb + off_ch(c) + U_BYTES, p.ssm_k + (5 * b + c) * SEQ, 4096, bars + 8 * B_HB);
        }
#pragma unroll
        for (int c = 0; c < 4; c++) mbar_expect_tx(bars + 8 * (B_U + c), c < 3 ? U_BYTES : 2 * U_BYTES);
        const uint4* usrc = g_U + 5 * b * U_PITCH;
        mbar_sleep(bars + 8 * B_USIG, 0);
        flag_wait(g_cnt + C_PREP + 32 * (b & 15), (epoch + 1) * NCTA);
        TS(23);
#pragma unroll
        for (int c = 0; c < 5; c++) {
          if (c == 3) mbar_sleep(bars + 8 * (B_U + 2), 0);
          bulk_load(sb + off_ch(c), usrc + c * U_PITCH, U_BYTES, bars + 8 * (B_U + (c < 3 ? c : 3)));
          TSIF(c == 0 || c == 4, 116 + (c >> 2));
        }
      }
      epoch = __shfl_sync(0xffffffffu, epoch, 0);
      if (lane < 8) {
        const int src = (b & ~7) | step_src(hg, lane);
        mbar_sleep(bars + 8 * B_OSIG, 0);
        TS(20);
        flag_wait(g_cnt + C_O + 32 * src, epoch + 1);
        if (lane >= 1 && lane < 4) bulk_load(sb + off_o(lane), g_O + src * 1280, O_BYTES, bars + 8 * (B_FULL2 + lane));
        __syncwarp(0xff);
        TS(21);
        if (lane == 5) bulk_load(sb + OFF_GATE, g_gate + 128 * r, 512, bars + 8 * (B_FULL2 + 5));
#pragma unroll 1
        for (int j = 4; j < 8; j++) {
          if (lane == j) {
            mbar_sleep(bars + 8 * (j < 6 ? B_C34 : B_EMPTY2 + j - 6), 0);
            if (RF_GATE && j == 6) mbar_sleep(bars + 8 * B_YSIG, 0);
            bulk_load(sb + off_o(j), g_O + src * 1280, O_BYTES, bars + 8 * (B_FULL2 + j));
          }
          __syncwarp(0xff);
        }
        TS(22);
      }
    } else if (w == 2) {
      mbar_sleep(bars + 8 * B_PREP, 0);
      flag_signal(g_cnt + C_PREP, 16, lane);
      TS(25);
      if (lane == 0) mbar_arrive(bars + 8 * B_USIG);
      mbar_sleep(bars + 8 * B_GATE, 0);
      if ((NOMB & 1) && lane == 0) asm volatile("fence.release.gpu;" ::: "memory");
      mbar_sleep(bars + 8 * B_ATTN, 0);
      if (lane == 0) {
        if (O_DEFER) mbar_sleep(bars + 8 * (B_U + 3), 0);
        asm volatile("cp.async.bulk.global.shared::cta.bulk_group [%0], [%1], 20480;\ncp.async.bulk.commit_group;\n"
                     "cp.async.bulk.wait_group 0;\nfence.proxy.async.global;" ::"l"(g_O + b * 1280), "r"(sb + OFF_OA) : "memory");
      }
      TS(74);
      if (!(NOMB & 1)) flag_signal(g_cnt + C_O + 32 * b, 1, lane);
      else if (lane == 0) flag_bump(g_cnt + C_O + 32 * b);
      TS(26);
      if (lane == 0) mbar_arrive(bars + 8 * B_OSIG);

    } else {
      if (lane == 0) {
        uint4* dst = g_WO + (hg * 8 + (r >> 1)) * 800 + (r & 1) * 80;
        mbar_sleep(bars + 8 * B_P1, 0);
        mbar_sleep(bars + 8 * WB_TRIG, 0);
        mbar_expect_tx(bars + 8 * B_WST, WO_BYTES / 2);
        tma_3d(sb + OFF_WS, &m.wo, 0, 40 * r, 5 * hg, bars + 8 * B_WST);
        mbar_sleep(bars + 8 * B_WST, 0);
        mbar_sleep(bars + 8 * WO_TRIG, 0);
#pragma unroll 1
        for (int n = 0; n < 5; n++)
          asm volatile("cp.async.bulk.global.shared::cta.bulk_group [%0], [%1], 1280;" ::"l"(dst + 160 * n), "r"(sb + OFF_WS + 1280 * n) : "memory");
        asm volatile("cp.async.bulk.commit_group;\ncp.async.bulk.wait_group 0;\nfence.proxy.async.global;" ::: "memory");
        if (!(NOMB & 4)) asm volatile("fence.release.gpu;" ::: "memory");
        flag_bump(g_cnt + C_W + 32 * hg);
        mbar_arrive(bars + 8 * B_WOP);
        TS(71);
#pragma unroll 1
        for (int c = 0; c < 5; c++) {
          mbar_sleep(bars + 8 * (B_YST + c), 0);
          asm volatile("cp.async.bulk.global.shared::cta.bulk_group [%0], [%1], 4096;\ncp.async.bulk.commit_group;"
                       ::"l"(g_Y + (5 * b + c) * Y_PITCH), "r"(sb + off_ch(c)) : "memory");
          if (c == 2) {
            asm volatile("cp.async.bulk.wait_group.read 0;" ::: "memory");
            mbar_arrive(bars + 8 * B_C34);
          }
        }
        asm volatile("cp.async.bulk.wait_group 0;\nfence.proxy.async.global;" ::: "memory");
        TS(75);
        if (!(NOMB & 2)) asm volatile("fence.release.gpu;" ::: "memory");
        flag_bump(g_cnt + C_Y + 32 * (b >> 4));
        TS(27);
        mbar_arrive(bars + 8 * B_YSIG);
        mbar_expect_tx(bars + 8 * B_YFULL, 20480);
        flag_wait(g_cnt + C_Y + 32 * hg, (lds32(sb + OFF_EPOCH) + 1) * 16);
        TS(24);
        tma_2d(sb + OFF_YT, &m.y, 128 * r, 80 * hg, bars + 8 * B_YFULL);
        tma_2d(sb + OFF_YT + 10240, &m.y, 128 * r + 64, 80 * hg, bars + 8 * B_YFULL);
      }
    }
  } else {
    asm volatile("setmaxnreg.inc.sync.aligned.u32 152;");
    if (wg < 2) {
      float acc[120];
#pragma unroll
      for (int i = 0; i < 120; i++) acc[i] = 0.f;
      const uint32_t da = desc_lo(sb + wg * 8192, 16), db = desc_lo(sb + ST_W, 8192), dc = desc_lo(sb + ST_WT, 2048);
      if (PW1) pin<120>(acc);
      if (PW1 == 2) mbar_wait(bars + 8 * B_FULL1, 0);
#pragma unroll 1
      for (int kb = 0; kb < 10; kb++) {
        mbar_wait(bars + 8 * (B_FULL1 + (kb & 3)), (kb >> 2) & 1);
        const uint32_t so = (kb & 3) * (STAGE_BYTES >> 4);
        wg_fence();
#pragma unroll
        for (int k = 0; k < 4; k++) {
          WgSST<192>::mma<HI_SW128, HI_SW128>(acc, da + so + 2 * k, db + so + 128 * k, 1);
          WgSST<48>::mma<HI_SW128, HI_SW32>(acc + 96, da + so + 2 * k, dc + so + 32 * k, 1);
        }
        wg_commit();
        wg_wait<1>();
        if (kb > 0 && lane == 0) mbar_arrive(bars + 8 * (kb == 4 ? B_E3 : B_EMPTY1 + ((kb - 1) & 3)));
      }
      mbar_wait(bars + 8 * B_EPOCH, 0);
      const uint32_t tag = lds32(sb + OFF_EPOCH) + 1;
      mbar_wait(bars + 8 * B_S3, 0);
      wg_wait<0>();
      pin<120>(acc);
      if (lane == 0) mbar_arrive(bars + 8 * B_P1);
      TSM(w == 0, 3 + wg);
      attention(acc, sb, b, wg, w, lane, tag);
    } else {
      const int tw = tid & 127, chl = 64 * (b & 1) + 8 * w + (lane >> 2);
      uint4* up = g_U + chl * U_PITCH + ((4 * (b >> 1) + (lane & 3)) ^ ((b >> 2) & 1));
      uint2 sw[10];
      uint32_t dv = 0;
      if (lane < 5) dv = __ldg(reinterpret_cast<const unsigned short*>(p.ssm_D) + 5 * b + lane);
#pragma unroll
      for (int i = 0; i < 10; i++) sw[i] = ldg64(reinterpret_cast<const uint2*>(p.shift_k) + chl + 128 * (i >> 1) + 32 * (i & 1));
      uint32_t tab[12];
      float tt[4];
      fft_tables(tab, tw);
      fft_twiddles(tt, tw);
      uint4 res[10];
#pragma unroll
      for (int i = 0; i < 10; i++) res[i] = make_uint4(0, 0, 0, 0);
#pragma unroll 1
      for (int slab = 0; slab < 5; slab++) {
#pragma unroll
        for (int i = 0; i < 8; i++) res[i] = res[i + 2];
        prep_slab(res + 8, sw, sb, slab, w, lane);
        TSIF(w == 0, 99 + 4 * slab);
#pragma unroll
        for (int i = 0; i < 8; i++) sw[i] = sw[i + 2];
      }
      TSIF(w == 0, 28);
      __syncwarp();
      if (lane == 0) mbar_arrive(bars + 8 * B_KVD + ((res[8].x ^ res[9].x) & p.zero));
      mbar_wait(bars + 8 * B_KVD, 0);
      fft_tables_store(tab, sb, tw);
      mbar_wait(bars + 8 * B_LAST, 0);
#pragma unroll
      for (int i = 0; i < 10; i++) up[(128 * (i >> 1) + 32 * (i & 1)) * U_PITCH] = res[i];
      __syncwarp();
      if (lane == 0) mbar_arrive(bars + 8 * B_PREP);
      TSIF(w == 0 && !U_TMA, 5);
      mbar_wait(bars + 8 * (G_AFTER ? B_USIG : B_LAST), 0);
      prep_gate(p, b, w, lane);
      __syncwarp();
      if (lane == 0) mbar_arrive(bars + 8 * B_GATE);
      TSIF(w == 0, 72);
      mbar_wait(bars + 8 * B_HB, 0);
      TSIF(w == 0, 2);
      const uint32_t ha = sb + U_BYTES + ((tw >> 3) * 16 + 8 + (tw & 7)) * 16;
      uint4 hv[5];
#pragma unroll
      for (int c = 0; c < 5; c++) hv[c] = lds128(ha + off_ch(c));
      __syncwarp();
#pragma unroll
      for (int c = 0; c < 5; c++) sts128((ha ^ 16) + off_ch(c), hv[c].x, hv[c].y, hv[c].z, hv[c].w);
      sts128(sb + OFF_TT + 16 * tw, __float_as_uint(tt[0]), __float_as_uint(tt[1]), __float_as_uint(tt[2]), __float_as_uint(tt[3]));
      if (tw < 5) asm volatile("st.shared.f32 [%0], %1;" ::"r"(sb + OFF_D + 4 * tw), "f"(bf_lo(dv) * 0.125f) : "memory");
      fence_async_smem();
      __syncwarp();
      if (lane == 0) mbar_arrive(bars + 8 * B_HA);
      TSIF(w == 0, 6);
    }

    FftConst fc;
    TSM(w == 0 && wg == 0, 104);
    mbar_wait(bars + 8 * B_HA, 0);
    fft_matrices(fc, sb, w, lane);
    TSM(w == 0 && wg == 0, 105);
    if (ATT_GATE && !H_EARLY) mbar_wait(bars + 8 * B_ATTN, 0);
    TSM(w == 0 && wg == 2, 124);
#pragma unroll 1
    for (int c = wg == 2 ? 0 : wg + 1; c < 5; c += !CH_W2 ? 3 : wg < 2 ? 5 : c ? 1 : 3) {
      conv_channel(fc, sb, c, wg, w, lane);
      if (lane == 0) mbar_arrive(bars + 8 * (B_YST + c));
      TSM(w == 0, 10 + c);
    }

    if (wg < 2) {
      const int g = lane >> 2;
      float acc[40];
#pragma unroll
      for (int i = 0; i < 40; i++) acc[i] = 0.f;
      const uint32_t da = desc_lo(sb + wg * 1024, 2048), db = desc_lo(sb, 2560);
      mbar_wait(bars + 8 * B_ATTN, 0);
      mbar_wait(bars + 8 * (B_YST + 3), 0);
      mbar_wait(bars + 8 * (B_YST + 4), 0);
      if (PW2) mbar_wait(bars + 8 * B_FULL2, 0);
      TSM(w == 0, 15 + wg);
#pragma unroll 1
      for (int j = 0; j < 8; j++) {
        mbar_wait(bars + 8 * (B_FULL2 + j), 0);
        const uint32_t oa = da + (off_o(j) >> 4), ob = db + (off_w(j) >> 4);
        wg_fence();
#pragma unroll
        for (int k = 0; k < 5; k++) WgSST<80>::mma<HI_NONE, HI_SW32>(acc, oa + 256 * k, ob + 32 * k, 1);
        wg_commit();
        wg_wait<1>();
        if (j >= 1 && j <= 4 && lane == 0) mbar_arrive(bars + 8 * (B_EMPTY2 + j - 1));
      }
      TSIF(w == 0 && wg == 0, 113);
      const int tr = 64 * wg + 16 * w + (lane & 15);
      const uint32_t fm = sb + OFF_QS + tr * 128, fx = (lane >> 4) ^ (tr & 7);
      const uint32_t ft = sb + OFF_QT + tr * 32 + (((lane >> 4) ^ (tr >> 2)) & 1) * 16;
      const float g0 = __uint_as_float(lds32(sb + OFF_GATE + (64 * wg + 16 * w + g) * 4));
      const float g1 = __uint_as_float(lds32(sb + OFF_GATE + (64 * wg + 16 * w + 8 + g) * 4));
      const uint32_t ga = pack2(g0, g0), gb = pack2(g1, g1);
      const uint32_t na = pack2(1.f - g0, 1.f - g0), nb = pack2(1.f - g1, 1.f - g1);

      wg_wait<0>();
      pin<40>(acc);
      TSM(w == 0, 17 + wg);
      uint32_t pb[20];
#pragma unroll
      for (int j = 0; j < 10; j++) {
        pb[2 * j] = bmul(na, pack2(acc[4 * j], acc[4 * j + 1]));
        pb[2 * j + 1] = bmul(nb, pack2(acc[4 * j + 2], acc[4 * j + 3]));
        asm volatile("" : "+r"(pb[2 * j]), "+r"(pb[2 * j + 1]));
      }
      const uint32_t ya = sb + OFF_YT + wg * 10240 + ((lane >> 4) * 8 + (lane & 7)) * 128 +
                          (((2 * w + (((lane >> 3) & 1) ^ wg)) ^ (lane & 7)) << 4);
      uint32_t qf[20];
      mbar_wait(bars + 8 * B_QF, 0);
#pragma unroll
      for (int j = 0; j < 5; j++) ldsm4(qf + 4 * j, j < 4 ? fm + ((fx ^ (2 * j)) << 4) : ft);
      mbar_wait(bars + 8 * B_YFULL, 0);
      TSM(w == 0 && wg == 0, 19);
#pragma unroll
      for (int j = 0; j < 5; j++) {
        uint32_t y[4];
        ldsm4t(y, ya + 2048 * j);
#pragma unroll
        for (int i = 0; i < 4; i++) qf[4 * j + i] = badd(bmul((i & 1) ? gb : ga, bmul(qf[4 * j + i], y[i])), pb[4 * j + i]);
      }
#pragma unroll
      for (int j = 0; j < 5; j++) stsm4(j < 4 ? fm + ((fx ^ (2 * j)) << 4) : ft, qf + 4 * j);
      fence_async_smem();
      __syncwarp();
      if (lane == 0) {
        const int row = 64 * wg + 16 * w;
        asm volatile("cp.async.bulk.tensor.2d.global.shared::cta.bulk_group [%0, {%2, %3}], [%1];"
                     ::"l"(&m.om), "r"(sb + OFF_QS + row * 128), "r"(80 * hg), "r"(128 * r + row) : "memory");
        asm volatile("cp.async.bulk.tensor.2d.global.shared::cta.bulk_group [%0, {%2, %3}], [%1];"
                     ::"l"(&m.ot), "r"(sb + OFF_QT + row * 32), "r"(80 * hg + 64), "r"(128 * r + row) : "memory");
        asm volatile("cp.async.bulk.commit_group;\ncp.async.bulk.wait_group.read 0;" ::: "memory");
      }
      TSM(true, 40 + 4 * wg + w);
      if (ENDBAR) asm volatile("bar.sync 15, 256;" ::: "memory");
    }
  }
}

typedef CUresult (*EncodeFn)(CUtensorMap*, CUtensorMapDataType, cuuint32_t, void*, const cuuint64_t*, const cuuint64_t*,
                             const cuuint32_t*, const cuuint32_t*, CUtensorMapInterleave, CUtensorMapSwizzle,
                             CUtensorMapL2promotion, CUtensorMapFloatOOBfill);

void encode(EncodeFn fn, CUtensorMap* tm, const void* base, int rank, const cuuint64_t* dims, const cuuint64_t* strides,
            const cuuint32_t* box, CUtensorMapSwizzle swz) {
  const cuuint32_t ones[3] = {1, 1, 1};
  fn(tm, CU_TENSOR_MAP_DATA_TYPE_BFLOAT16, rank, const_cast<void*>(base), dims, strides, box, ones,
     CU_TENSOR_MAP_INTERLEAVE_NONE, swz, CU_TENSOR_MAP_L2_PROMOTION_L2_128B, CU_TENSOR_MAP_FLOAT_OOB_FILL_NONE);
}

}

extern "C" void kernel_launch(void* const* d_in, const int* in_sizes, int n_in, void* d_out, int out_size) {
  (void)in_sizes; (void)n_in; (void)out_size;
  Params p;
  p.q = (const __nv_bfloat16*)d_in[0];
  p.k = (const __nv_bfloat16*)d_in[1];
  p.v = (const __nv_bfloat16*)d_in[2];
  p.shift_k = (const __nv_bfloat16*)d_in[3];
  p.ssm_k = (const __nv_bfloat16*)d_in[4];
  p.ssm_D = (const __nv_bfloat16*)d_in[5];
  p.wqkv = (const __nv_bfloat16*)d_in[7];
  p.wo = (const __nv_bfloat16*)d_in[8];
  p.gate_w = (const __nv_bfloat16*)d_in[9];
  p.out = (__nv_bfloat16*)d_out;
  p.zero = 0;

  static EncodeFn fn = nullptr;
  static void *yaddr = nullptr, *uaddr = nullptr;
  if (!fn) {
    cudaDriverEntryPointQueryResult qr;
    void* f = nullptr;
    cudaGetDriverEntryPoint("cuTensorMapEncodeTiled", &f, cudaEnableDefault, &qr);
    fn = (EncodeFn)f;
    cudaGetSymbolAddress(&yaddr, g_Y);
    cudaGetSymbolAddress(&uaddr, g_U);
    cudaFuncSetAttribute(fused_kernel, cudaFuncAttributeMaxDynamicSharedMemorySize, SMEM_BYTES);
  }
  Maps m;
  {
    const cuuint64_t dims[3] = {640, 1024, 2}, st[2] = {2560, 1280};
    const cuuint32_t box[3] = {64, 64, 2};
    encode(fn, &m.x, p.q, 3, dims, st, box, CU_TENSOR_MAP_SWIZZLE_128B);
  }
  {
    const cuuint64_t dims[3] = {640, 640, 3}, st[2] = {3840, 1280};
    const cuuint32_t box[3] = {64, 64, 3}, boxt[3] = {16, 64, 3};
    encode(fn, &m.wm, p.wqkv, 3, dims, st, box, CU_TENSOR_MAP_SWIZZLE_128B);
    encode(fn, &m.wt, p.wqkv, 3, dims, st, boxt, CU_TENSOR_MAP_SWIZZLE_32B);
  }
  {
    const cuuint64_t dims[3] = {64, 2048, 10}, st[2] = {1280, 128};
    const cuuint32_t boxk[3] = {64, 35, 1}, boxv[3] = {64, 32, 1};
    encode(fn, &m.k, p.k, 3, dims, st, boxk, CU_TENSOR_MAP_SWIZZLE_128B);
    encode(fn, &m.v, p.v, 3, dims, st, boxv, CU_TENSOR_MAP_SWIZZLE_128B);
  }
  {
    const cuuint64_t dims[3] = {16, 640, 40}, st[2] = {1280, 32};
    const cuuint32_t box[3] = {16, 40, 5};
    encode(fn, &m.wo, p.wo, 3, dims, st, box, CU_TENSOR_MAP_SWIZZLE_32B);
  }
  {
    const cuuint64_t dims[2] = {2048, 640}, st[1] = {Y_PITCH * 16};
    const cuuint32_t box[2] = {64, 80};
    encode(fn, &m.y, yaddr, 2, dims, st, box, CU_TENSOR_MAP_SWIZZLE_128B);
    const cuuint64_t stu[1] = {U_PITCH * 16};
    const cuuint32_t boxu[2] = {32, 64};
    encode(fn, &m.u, uaddr, 2, dims, stu, boxu, CU_TENSOR_MAP_SWIZZLE_NONE);
  }
  {
    const cuuint64_t dims[2] = {640, 2048}, st[1] = {1280};
    const cuuint32_t bqm[2] = {64, 128}, bqt[2] = {16, 128}, bom[2] = {64, 16}, bot[2] = {16, 16};
    encode(fn, &m.qm, p.q, 2, dims, st, bqm, CU_TENSOR_MAP_SWIZZLE_128B);
    encode(fn, &m.qt, p.q, 2, dims, st, bqt, CU_TENSOR_MAP_SWIZZLE_32B);
    encode(fn, &m.om, p.out, 2, dims, st, bom, CU_TENSOR_MAP_SWIZZLE_128B);
    encode(fn, &m.ot, p.out, 2, dims, st, bot, CU_TENSOR_MAP_SWIZZLE_32B);
  }
  fused_kernel<<<NCTA, NTHR, SMEM_BYTES>>>(m, p);
}
```

```cpp
#include <cuda.h>
#include <cuda_bf16.h>
#include <cuda_runtime.h>
#include <stdint.h>

namespace {

constexpr int SEQ = 2048, DIM = 640, NCTA = 128, NTHR = 512;

#define TRIG_KB 9
#define KV_KB 2
#define DEV_EXIT 0
#define ATT_GATE 1
#define G_AFTER 0
#define FENCE_LO 0
#define FENCE_HI 0
#define PW1 2
#define PW2 1
#define ENDBAR 0
#define PAD_KB 0
#define Y_ALIAS 1
#define H_EARLY 1
#define NOMB 0
#define SRC_ROT 0
#define WAIT_NS 0
#define WB_TRIG B_USIG
#define G_POS 0
#define TAILF 1
#define T_ISSUE 384
#define T_PF 416
#define T_INIT 448
#define ATT_MERGE 0
#define BMAP 1
#define PRE2 1
#define KV_MIX 0
#define O_DEFER 0
#define TASK0 0xDA2
#define TASK1 0x5B3
#define TASK2 0xC941
#define HALO_FIRST 1
#define PREV_EARLY 0
#define SLEEP_NS 0
#define SLEEP_P1 0
#define ACQ 0
#define U_TMA 0
#define U_GATE 0
#define RF_GATE 0
#define WO_TRIG B_WST
#define WL_TRIG B_WOP
#define WO_GATE 1

constexpr uint32_t STAGE_BYTES = 47104, ST_W = 16384, ST_WT = 40960;
constexpr uint32_t O_BYTES = 20480, WO_BYTES = 12800;
constexpr uint32_t OFF_OA = 0;
constexpr uint32_t OFF_QS = 3 * O_BYTES, OFF_QT = OFF_QS + 16384;
constexpr uint32_t OFF_WC = 81920;
constexpr uint32_t OFF_WA = 94720;
constexpr uint32_t OFF_GATE = 145920;
constexpr uint32_t OFF_TT = 146432;
constexpr uint32_t OFF_KVX = 148480;
constexpr uint32_t OFF_CH3 = 163840;
constexpr uint32_t CH_BYTES = 12288, U_BYTES = 4096;
constexpr uint32_t OFF_FT = 225280, OFF_GT = 229376;
constexpr uint32_t OFF_CH0 = 188416;
constexpr uint32_t OFF_KVS = OFF_CH0, KVS_V = 4480, KVS_BYTES = 8576;
constexpr uint32_t OFF_WS = OFF_WA;
__device__ __forceinline__ uint32_t off_us(int s) { return OFF_CH0 + 4096 * ((0x65320 >> (4 * s)) & 7); }
constexpr uint32_t OFF_YT = 163840;
constexpr uint32_t OFF_BAR = 231936;
constexpr uint32_t SMEM_BYTES = OFF_BAR + 512;

enum : uint32_t {
  B_FULL1 = 0, B_EMPTY1 = 4, B_S3 = 7, B_FULL2 = 52, B_EMPTY2 = 13, B_U = 8, B_GATE = 12, B_HA = 19, B_HB = 20,
  B_ATTN = 21, B_C34 = 22, B_CONV = 23, B_YFULL = 24, B_EPOCH = 25, B_PREP = 26, B_P1 = 27, B_LAST = 28,
  B_E3 = 29, B_OSIG = 30, B_WOP = 31, B_USIG = 32, B_WST = 33, B_KV = 34, B_KVD = 39, B_QF = 17, B_YST = 40,
  B_US = 45, B_H = 45, B_YSIG = 50
};
constexpr uint32_t OFF_EPOCH = OFF_BAR + 8 * 51, OFF_D = OFF_BAR + 8 * 60;
__device__ __forceinline__ uint32_t off_o(int j) { return j < 4 ? OFF_OA + j * O_BYTES : j < 6 ? OFF_CH0 + (j - 4) * O_BYTES : OFF_OA + (j - 6) * O_BYTES; }
__device__ __forceinline__ uint32_t off_w(int j) { return j < 4 ? OFF_WA + j * WO_BYTES : j == 4 ? OFF_KVX : j == 5 ? OFF_WC : OFF_WA + (j - 6) * WO_BYTES; }
__device__ __forceinline__ int step_src(int hg, int j) { return SRC_ROT ? (hg + j) & 7 : j == 0 ? hg : j <= hg ? j - 1 : j; }
__device__ __forceinline__ bool tail_first(int hg) { return TAILF && (hg & 3) == 3; }
__device__ __forceinline__ uint32_t off_ch(int c) { return (c < 3 ? OFF_CH0 : OFF_CH3 - 3 * CH_BYTES) + c * CH_BYTES; }

#define U_PITCH 264
__device__ __align__(1024) uint4 g_U[DIM * U_PITCH];
__device__ uint4 g_O[NCTA * 1280];
#define g_Y g_U
constexpr int Y_PITCH = U_PITCH;
__device__ uint4 g_WO[64 * 800];
__device__ uint4 g_halo[NCTA * 2 * 7 * 32];
__device__ float g_gate[SEQ + PAD_KB * 256];
__device__ unsigned g_cnt[32 * (1 + 2 * 16 + 8 + NCTA)];
constexpr int C_LAUNCH = 0, C_PREP = 32, C_Y = 32 * 17, C_W = 32 * 33, C_O = 32 * 41;

#define TSM(cond, slot) do { } while (0)
#define TSIF(cond, slot) do { if (__LINE__ >= FENCE_LO && __LINE__ < FENCE_HI) sched_fence(); } while (0)
__device__ __forceinline__ void sched_fence() {
  asm volatile("{\n.reg .pred p;\n.reg .u32 c;\nmov.u32 c, %%clock;\nsetp.eq.u32 p, c, 0;\n@p st.shared.u32 [%0], c;\n}"
               ::"r"(1024 + OFF_EPOCH + 4) : "memory");
}
#define TS(slot) TSIF(true, slot)

struct Params {
  const __nv_bfloat16 *q, *k, *v, *shift_k, *ssm_k, *ssm_D, *wqkv, *wo, *gate_w;
  __nv_bfloat16* out;
  uint32_t zero;
};

#define POLL_NS 0
constexpr int SPIN_LIMIT = 1 << 17;

__device__ __forceinline__ void mbar_init(uint32_t bar, uint32_t count) {
  asm volatile("mbarrier.init.shared::cta.b64 [%0], %1;" ::"r"(bar), "r"(count) : "memory");
}
__device__ __forceinline__ void mbar_expect_tx(uint32_t bar, uint32_t bytes) {
  asm volatile("mbarrier.arrive.expect_tx.shared::cta.b64 _, [%0], %1;" ::"r"(bar), "r"(bytes) : "memory");
}
__device__ __forceinline__ void mbar_arrive(uint32_t bar) {
  asm volatile("mbarrier.arrive.shared::cta.b64 _, [%0];" ::"r"(bar) : "memory");
}
__device__ __forceinline__ void mbar_wait(uint32_t bar, uint32_t parity) {
  uint32_t ok;
  int spins = 0;
  do {
    if (WAIT_NS)
      asm volatile("{\n.reg .pred p;\nmbarrier.try_wait.parity.shared::cta.b64 p, [%1], %2, %3;\nselp.b32 %0, 1, 0, p;\n}"
                   : "=r"(ok) : "r"(bar), "r"(parity), "r"(WAIT_NS) : "memory");
    else
      asm volatile("{\n.reg .pred p;\nmbarrier.try_wait.parity.shared::cta.b64 p, [%1], %2;\nselp.b32 %0, 1, 0, p;\n}"
                   : "=r"(ok) : "r"(bar), "r"(parity) : "memory");
    if (++spins > SPIN_LIMIT) break;
  } while (!ok);
}
__device__ __forceinline__ void mbar_sleep(uint32_t bar, uint32_t parity) {
  uint32_t ok;
  int spins = 0;
  do {
    if (SLEEP_NS)
      asm volatile("{\n.reg .pred p;\nmbarrier.try_wait.parity.shared::cta.b64 p, [%1], %2, %3;\nselp.b32 %0, 1, 0, p;\n}"
                   : "=r"(ok) : "r"(bar), "r"(parity), "r"(SLEEP_NS) : "memory");
    else
      asm volatile("{\n.reg .pred p;\nmbarrier.try_wait.parity.shared::cta.b64 p, [%1], %2;\nselp.b32 %0, 1, 0, p;\n}"
                   : "=r"(ok) : "r"(bar), "r"(parity) : "memory");
    if (++spins > SPIN_LIMIT) break;
  } while (!ok);
}
__device__ __forceinline__ void flag_poll(const unsigned* p, unsigned target) {
  unsigned v;
  int spins = 0;
  do {
    if (POLL_NS && spins) __nanosleep(POLL_NS);
    asm volatile("ld.relaxed.gpu.global.u32 %0, [%1];" : "=r"(v) : "l"(p) : "memory");
    if (++spins > SPIN_LIMIT) break;
  } while ((int)(v - target) < 0);
}
__device__ __forceinline__ void flag_wait(const unsigned* p, unsigned target) {
  flag_poll(p, target);
  if (ACQ) asm volatile("fence.acquire.gpu;\nfence.proxy.async.global;" ::: "memory");
}
__device__ __forceinline__ void flag_signal(unsigned* p, int n, int lane) {
  if (lane == 0) asm volatile("fence.release.gpu;" ::: "memory");
  __syncwarp();
  if (lane < n) asm volatile("red.relaxed.gpu.global.add.u32 [%0], 1;" ::"l"(p + 32 * lane) : "memory");
}
__device__ __forceinline__ void flag_bump(unsigned* p) {
  asm volatile("red.relaxed.gpu.global.add.u32 [%0], 1;" ::"l"(p) : "memory");
}
__device__ __forceinline__ void fence_async_smem() { asm volatile("fence.proxy.async.shared::cta;" ::: "memory"); }
__device__ __forceinline__ void wg_sync(int id) { asm volatile("bar.sync %0, 128;" ::"r"(id) : "memory"); }

__device__ __forceinline__ void tma_2d(uint32_t dst, const CUtensorMap* tm, int c0, int c1, uint32_t bar) {
  asm volatile("cp.async.bulk.tensor.2d.shared::cluster.global.mbarrier::complete_tx::bytes [%0], [%1, {%3, %4}], [%2];"
               ::"r"(dst), "l"(tm), "r"(bar), "r"(c0), "r"(c1) : "memory");
}
__device__ __forceinline__ void tma_3d(uint32_t dst, const CUtensorMap* tm, int c0, int c1, int c2, uint32_t bar) {
  asm volatile("cp.async.bulk.tensor.3d.shared::cluster.global.mbarrier::complete_tx::bytes [%0], [%1, {%3, %4, %5}], [%2];"
               ::"r"(dst), "l"(tm), "r"(bar), "r"(c0), "r"(c1), "r"(c2) : "memory");
}
__device__ __forceinline__ void bulk_load(uint32_t dst, const void* src, uint32_t bytes, uint32_t bar) {
  asm volatile("cp.async.bulk.shared::cluster.global.mbarrier::complete_tx::bytes [%0], [%1], %2, [%3];"
               ::"r"(dst), "l"(src), "r"(bytes), "r"(bar) : "memory");
}
__device__ __forceinline__ void tm_prefetch(const CUtensorMap* tm) {
  asm volatile("prefetch.tensormap [%0];" ::"l"(tm) : "memory");
}

__device__ __forceinline__ void wg_fence() { asm volatile("wgmma.fence.sync.aligned;" ::: "memory"); }
__device__ __forceinline__ void wg_commit() { asm volatile("wgmma.commit_group.sync.aligned;" ::: "memory"); }
template <int N> __device__ __forceinline__ void wg_wait() { asm volatile("wgmma.wait_group.sync.aligned %0;" ::"n"(N) : "memory"); }
__device__ __forceinline__ uint32_t desc_lo(uint32_t addr, uint32_t lbo) { return ((addr & 0x3FFFF) >> 4) | ((lbo >> 4) << 16); }
constexpr uint32_t desc_hi(uint32_t sbo, uint32_t swz) { return (sbo >> 4) | (swz << 30); }
constexpr uint32_t HI_SW128 = desc_hi(1024, 1), HI_SW64 = desc_hi(512, 2), HI_SW32 = desc_hi(256, 3), HI_NONE = desc_hi(128, 0);
template <int N> __device__ __forceinline__ void pin(float* d) {
#pragma unroll
  for (int i = 0; i < N; i++) asm volatile("" : "+f"(d[i])::"memory");
}

__device__ __forceinline__ uint32_t lds32(uint32_t a) {
  uint32_t v;
  asm volatile("ld.volatile.shared.u32 %0, [%1];" : "=r"(v) : "r"(a) : "memory");
  return v;
}
__device__ __forceinline__ uint4 ldg128(const void* a) {
  uint4 v;
  asm volatile("ld.global.nc.v4.u32 {%0, %1, %2, %3}, [%4];" : "=r"(v.x), "=r"(v.y), "=r"(v.z), "=r"(v.w) : "l"(a) : "memory");
  return v;
}
__device__ __forceinline__ uint2 ldg64(const void* a) {
  uint2 v;
  asm volatile("ld.global.nc.v2.u32 {%0, %1}, [%2];" : "=r"(v.x), "=r"(v.y) : "l"(a) : "memory");
  return v;
}
__device__ __forceinline__ void ldsm4(uint32_t* r, uint32_t a) {
  asm volatile("ldmatrix.sync.aligned.m8n8.x4.shared.b16 {%0, %1, %2, %3}, [%4];"
               : "=r"(r[0]), "=r"(r[1]), "=r"(r[2]), "=r"(r[3]) : "r"(a) : "memory");
}
__device__ __forceinline__ void ldsm4t(uint32_t* r, uint32_t a) {
  asm volatile("ldmatrix.sync.aligned.m8n8.x4.trans.shared.b16 {%0, %1, %2, %3}, [%4];"
               : "=r"(r[0]), "=r"(r[1]), "=r"(r[2]), "=r"(r[3]) : "r"(a) : "memory");
}
__device__ __forceinline__ uint4 lds128(uint32_t a) {
  uint4 v;
  asm volatile("ld.shared.v4.u32 {%0, %1, %2, %3}, [%4];" : "=r"(v.x), "=r"(v.y), "=r"(v.z), "=r"(v.w) : "r"(a) : "memory");
  return v;
}
__device__ __forceinline__ void sts128(uint32_t a, uint32_t x, uint32_t y, uint32_t z, uint32_t w) {
  asm volatile("st.shared.v4.u32 [%0], {%1, %2, %3, %4};" ::"r"(a), "r"(x), "r"(y), "r"(z), "r"(w) : "memory");
}
__device__ __forceinline__ void stsm4(uint32_t a, const uint32_t* r) {
  asm volatile("stmatrix.sync.aligned.m8n8.x4.shared.b16 [%0], {%1, %2, %3, %4};" ::"r"(a), "r"(r[0]), "r"(r[1]), "r"(r[2]), "r"(r[3]) : "memory");
}
__device__ __forceinline__ void stsm4t(uint32_t a, const uint32_t* r) {
  asm volatile("stmatrix.sync.aligned.m8n8.x4.trans.shared.b16 [%0], {%1, %2, %3, %4};" ::"r"(a), "r"(r[0]), "r"(r[1]), "r"(r[2]), "r"(r[3]) : "memory");
}
__device__ __forceinline__ uint32_t pack2(float lo, float hi) {
  uint32_t r;
  asm("cvt.rn.bf16x2.f32 %0, %1, %2;" : "=r"(r) : "f"(hi), "f"(lo));
  return r;
}
__device__ __forceinline__ uint32_t movm(uint32_t a) {
  uint32_t d;
  asm volatile("movmatrix.sync.aligned.m8n8.trans.b16 %0, %1;" : "=r"(d) : "r"(a));
  return d;
}
__device__ __forceinline__ uint32_t bmul(uint32_t a, uint32_t b) {
  uint32_t d;
  asm("mul.rn.bf16x2 %0, %1, %2;" : "=r"(d) : "r"(a), "r"(b));
  return d;
}
__device__ __forceinline__ uint32_t badd(uint32_t a, uint32_t b) {
  uint32_t d;
  asm("add.rn.bf16x2 %0, %1, %2;" : "=r"(d) : "r"(a), "r"(b));
  return d;
}
__device__ __forceinline__ float bf_lo(uint32_t x) { return __uint_as_float(x << 16); }
__device__ __forceinline__ float bf_hi(uint32_t x) { return __uint_as_float(x & 0xFFFF0000u); }
__device__ __forceinline__ float ex2(float x) {
  float y;
  asm("ex2.approx.ftz.f32 %0, %1;" : "=f"(y) : "f"(x));
  return y;
}
__device__ __forceinline__ float rcp(float x) {
  float y;
  asm("rcp.approx.ftz.f32 %0, %1;" : "=f"(y) : "f"(x));
  return y;
}
__device__ __forceinline__ void mma16816(float* d, uint32_t a0, uint32_t a1, uint32_t a2, uint32_t a3, uint32_t b0, uint32_t b1) {
  asm volatile("mma.sync.aligned.m16n8k16.row.col.f32.bf16.bf16.f32 {%0, %1, %2, %3}, {%4, %5, %6, %7}, {%8, %9}, {%0, %1, %2, %3};"
               : "+f"(d[0]), "+f"(d[1]), "+f"(d[2]), "+f"(d[3])
               : "r"(a0), "r"(a1), "r"(a2), "r"(a3), "r"(b0), "r"(b1));
}
__device__ __forceinline__ void mma1688(float* d, uint32_t a0, uint32_t a1, uint32_t b0) {
  asm volatile("mma.sync.aligned.m16n8k8.row.col.f32.bf16.bf16.f32 {%0, %1, %2, %3}, {%4, %5}, {%6}, {%0, %1, %2, %3};"
               : "+f"(d[0]), "+f"(d[1]), "+f"(d[2]), "+f"(d[3])
               : "r"(a0), "r"(a1), "r"(b0));
}

template <int N> struct WgRS;
template <int N> struct WgSST;
template <> struct WgRS<32> {
  template <uint32_t HB>
  static __device__ __forceinline__ void mma(float* d, const uint32_t* a, uint32_t db) {
    asm volatile("{\n.reg .pred p;\n.reg .b64 db;\nsetp.ne.b32 p, %22, 0;\n"
      "mov.b64 db, {%20, %21};\n"
      "wgmma.mma_async.sync.aligned.m64n32k16.f32.bf16.bf16 {"
      "%0, %1, %2, %3, %4, %5, %6, %7, %8, %9, %10, %11, %12, %13, %14, %15"
      "}, {%16, %17, %18, %19}, db, p, 1, 1, 1;\n}\n"
      : "+f"(d[0]), "+f"(d[1]), "+f"(d[2]), "+f"(d[3]), "+f"(d[4]), "+f"(d[5]), "+f"(d[6]), "+f"(d[7]),
        "+f"(d[8]), "+f"(d[9]), "+f"(d[10]), "+f"(d[11]), "+f"(d[12]), "+f"(d[13]), "+f"(d[14]), "+f"(d[15])
      : "r"(a[0]), "r"(a[1]), "r"(a[2]), "r"(a[3]), "r"(db), "n"(HB), "n"(1));
  }
  template <uint32_t HB>
  static __device__ __forceinline__ void set(float* d, const uint32_t* a, uint32_t db) {
    asm volatile("{\n.reg .pred p;\n.reg .b64 db;\nsetp.ne.b32 p, %22, 0;\n"
      "mov.b64 db, {%20, %21};\n"
      "wgmma.mma_async.sync.aligned.m64n32k16.f32.bf16.bf16 {"
      "%0, %1, %2, %3, %4, %5, %6, %7, %8, %9, %10, %11, %12, %13, %14, %15"
      "}, {%16, %17, %18, %19}, db, p, 1, 1, 1;\n}\n"
      : "=f"(d[0]), "=f"(d[1]), "=f"(d[2]), "=f"(d[3]), "=f"(d[4]), "=f"(d[5]), "=f"(d[6]), "=f"(d[7]),
        "=f"(d[8]), "=f"(d[9]), "=f"(d[10]), "=f"(d[11]), "=f"(d[12]), "=f"(d[13]), "=f"(d[14]), "=f"(d[15])
      : "r"(a[0]), "r"(a[1]), "r"(a[2]), "r"(a[3]), "r"(db), "n"(HB), "n"(0));
  }
};
template <> struct WgRS<64> {
  template <uint32_t HB>
  static __device__ __forceinline__ void mma(float* d, const uint32_t* a, uint32_t db) {
    asm volatile("{\n.reg .pred p;\n.reg .b64 db;\nsetp.ne.b32 p, %38, 0;\n"
      "mov.b64 db, {%36, %37};\n"
      "wgmma.mma_async.sync.aligned.m64n64k16.f32.bf16.bf16 {"
      "%0, %1, %2, %3, %4, %5, %6, %7, %8, %9, %10, %11, %12, %13, %14, %15, "
      "%16, %17, %18, %19, %20, %21, %22, %23, %24, %25, %26, %27, %28, %29, %30, %31"
      "}, {%32, %33, %34, %35}, db, p, 1, 1, 1;\n}\n"
      : "+f"(d[0]), "+f"(d[1]), "+f"(d[2]), "+f"(d[3]), "+f"(d[4]), "+f"(d[5]), "+f"(d[6]), "+f"(d[7]),
        "+f"(d[8]), "+f"(d[9]), "+f"(d[10]), "+f"(d[11]), "+f"(d[12]), "+f"(d[13]), "+f"(d[14]), "+f"(d[15]),
        "+f"(d[16]), "+f"(d[17]), "+f"(d[18]), "+f"(d[19]), "+f"(d[20]), "+f"(d[21]), "+f"(d[22]), "+f"(d[23]),
        "+f"(d[24]), "+f"(d[25]), "+f"(d[26]), "+f"(d[27]), "+f"(d[28]), "+f"(d[29]), "+f"(d[30]), "+f"(d[31])
      : "r"(a[0]), "r"(a[1]), "r"(a[2]), "r"(a[3]), "r"(db), "n"(HB), "n"(1));
  }
  template <uint32_t HB>
  static __device__ __forceinline__ void set(float* d, const uint32_t* a, uint32_t db) {
    asm volatile("{\n.reg .pred p;\n.reg .b64 db;\nsetp.ne.b32 p, %38, 0;\n"
      "mov.b64 db, {%36, %37};\n"
      "wgmma.mma_async.sync.aligned.m64n64k16.f32.bf16.bf16 {"
      "%0, %1, %2, %3, %4, %5, %6, %7, %8, %9, %10, %11, %12, %13, %14, %15, "
      "%16, %17, %18, %19, %20, %21, %22, %23, %24, %25, %26, %27, %28, %29, %30, %31"
      "}, {%32, %33, %34, %35}, db, p, 1, 1, 1;\n}\n"
      : "=f"(d[0]), "=f"(d[1]), "=f"(d[2]), "=f"(d[3]), "=f"(d[4]), "=f"(d[5]), "=f"(d[6]), "=f"(d[7]),
        "=f"(d[8]), "=f"(d[9]), "=f"(d[10]), "=f"(d[11]), "=f"(d[12]), "=f"(d[13]), "=f"(d[14]), "=f"(d[15]),
        "=f"(d[16]), "=f"(d[17]), "=f"(d[18]), "=f"(d[19]), "=f"(d[20]), "=f"(d[21]), "=f"(d[22]), "=f"(d[23]),
        "=f"(d[24]), "=f"(d[25]), "=f"(d[26]), "=f"(d[27]), "=f"(d[28]), "=f"(d[29]), "=f"(d[30]), "=f"(d[31])
      : "r"(a[0]), "r"(a[1]), "r"(a[2]), "r"(a[3]), "r"(db), "n"(HB), "n"(0));
  }
};
template <> struct WgSST<48> {
  template <uint32_t HA, uint32_t HB>
  static __device__ __forceinline__ void mma(float* d, uint32_t da, uint32_t db, int sc) {
    asm volatile("{\n.reg .pred p;\n.reg .b64 da, db;\nsetp.ne.b32 p, %28, 0;\n"
      "mov.b64 da, {%24, %25};\nmov.b64 db, {%26, %27};\n"
      "wgmma.mma_async.sync.aligned.m64n48k16.f32.bf16.bf16 {"
      "%0, %1, %2, %3, %4, %5, %6, %7, %8, %9, %10, %11, %12, %13, %14, %15, "
      "%16, %17, %18, %19, %20, %21, %22, %23"
      "}, da, db, p, 1, 1, 0, 1;\n}\n"
      : "+f"(d[0]), "+f"(d[1]), "+f"(d[2]), "+f"(d[3]), "+f"(d[4]), "+f"(d[5]), "+f"(d[6]), "+f"(d[7]),
        "+f"(d[8]), "+f"(d[9]), "+f"(d[10]), "+f"(d[11]), "+f"(d[12]), "+f"(d[13]), "+f"(d[14]), "+f"(d[15]),
        "+f"(d[16]), "+f"(d[17]), "+f"(d[18]), "+f"(d[19]), "+f"(d[20]), "+f"(d[21]), "+f"(d[22]), "+f"(d[23])
      : "r"(da), "n"(HA), "r"(db), "n"(HB), "r"(sc));
  }
};
template <> struct WgSST<80> {
  template <uint32_t HA, uint32_t HB>
  static __device__ __forceinline__ void mma(float* d, uint32_t da, uint32_t db, int sc) {
    asm volatile("{\n.reg .pred p;\n.reg .b64 da, db;\nsetp.ne.b32 p, %44, 0;\n"
      "mov.b64 da, {%40, %41};\nmov.b64 db, {%42, %43};\n"
      "wgmma.mma_async.sync.aligned.m64n80k16.f32.bf16.bf16 {"
      "%0, %1, %2, %3, %4, %5, %6, %7, %8, %9, %10, %11, %12, %13, %14, %15, "
      "%16, %17, %18, %19, %20, %21, %22, %23, %24, %25, %26, %27, %28, %29, %30, %31, "
      "%32, %33, %34, %35, %36, %37, %38, %39"
      "}, da, db, p, 1, 1, 0, 1;\n}\n"
      : "+f"(d[0]), "+f"(d[1]), "+f"(d[2]), "+f"(d[3]), "+f"(d[4]), "+f"(d[5]), "+f"(d[6]), "+f"(d[7]),
        "+f"(d[8]), "+f"(d[9]), "+f"(d[10]), "+f"(d[11]), "+f"(d[12]), "+f"(d[13]), "+f"(d[14]), "+f"(d[15]),
        "+f"(d[16]), "+f"(d[17]), "+f"(d[18]), "+f"(d[19]), "+f"(d[20]), "+f"(d[21]), "+f"(d[22]), "+f"(d[23]),
        "+f"(d[24]), "+f"(d[25]), "+f"(d[26]), "+f"(d[27]), "+f"(d[28]), "+f"(d[29]), "+f"(d[30]), "+f"(d[31]),
        "+f"(d[32]), "+f"(d[33]), "+f"(d[34]), "+f"(d[35]), "+f"(d[36]), "+f"(d[37]), "+f"(d[38]), "+f"(d[39])
      : "r"(da), "n"(HA), "r"(db), "n"(HB), "r"(sc));
  }
};
template <> struct WgSST<192> {
  template <uint32_t HA, uint32_t HB>
  static __device__ __forceinline__ void mma(float* d, uint32_t da, uint32_t db, int sc) {
    asm volatile("{\n.reg .pred p;\n.reg .b64 da, db;\nsetp.ne.b32 p, %100, 0;\n"
      "mov.b64 da, {%96, %97};\nmov.b64 db, {%98, %99};\n"
      "wgmma.mma_async.sync.aligned.m64n192k16.f32.bf16.bf16 {"
      "%0, %1, %2, %3, %4, %5, %6, %7, %8, %9, %10, %11, %12, %13, %14, %15, "
      "%16, %17, %18, %19, %20, %21, %22, %23, %24, %25, %26, %27, %28, %29, %30, %31, "
      "%32, %33, %34, %35, %36, %37, %38, %39, %40, %41, %42, %43, %44, %45, %46, %47, "
      "%48, %49, %50, %51, %52, %53, %54, %55, %56, %57, %58, %59, %60, %61, %62, %63, "
      "%64, %65, %66, %67, %68, %69, %70, %71, %72, %73, %74, %75, %76, %77, %78, %79, "
      "%80, %81, %82, %83, %84, %85, %86, %87, %88, %89, %90, %91, %92, %93, %94, %95"
      "}, da, db, p, 1, 1, 0, 1;\n}\n"
      : "+f"(d[0]), "+f"(d[1]), "+f"(d[2]), "+f"(d[3]), "+f"(d[4]), "+f"(d[5]), "+f"(d[6]), "+f"(d[7]),
        "+f"(d[8]), "+f"(d[9]), "+f"(d[10]), "+f"(d[11]), "+f"(d[12]), "+f"(d[13]), "+f"(d[14]), "+f"(d[15]),
        "+f"(d[16]), "+f"(d[17]), "+f"(d[18]), "+f"(d[19]), "+f"(d[20]), "+f"(d[21]), "+f"(d[22]), "+f"(d[23]),
        "+f"(d[24]), "+f"(d[25]), "+f"(d[26]), "+f"(d[27]), "+f"(d[28]), "+f"(d[29]), "+f"(d[30]), "+f"(d[31]),
        "+f"(d[32]), "+f"(d[33]), "+f"(d[34]), "+f"(d[35]), "+f"(d[36]), "+f"(d[37]), "+f"(d[38]), "+f"(d[39]),
        "+f"(d[40]), "+f"(d[41]), "+f"(d[42]), "+f"(d[43]), "+f"(d[44]), "+f"(d[45]), "+f"(d[46]), "+f"(d[47]),
        "+f"(d[48]), "+f"(d[49]), "+f"(d[50]), "+f"(d[51]), "+f"(d[52]), "+f"(d[53]), "+f"(d[54]), "+f"(d[55]),
        "+f"(d[56]), "+f"(d[57]), "+f"(d[58]), "+f"(d[59]), "+f"(d[60]), "+f"(d[61]), "+f"(d[62]), "+f"(d[63]),
        "+f"(d[64]), "+f"(d[65]), "+f"(d[66]), "+f"(d[67]), "+f"(d[68]), "+f"(d[69]), "+f"(d[70]), "+f"(d[71]),
        "+f"(d[72]), "+f"(d[73]), "+f"(d[74]), "+f"(d[75]), "+f"(d[76]), "+f"(d[77]), "+f"(d[78]), "+f"(d[79]),
        "+f"(d[80]), "+f"(d[81]), "+f"(d[82]), "+f"(d[83]), "+f"(d[84]), "+f"(d[85]), "+f"(d[86]), "+f"(d[87]),
        "+f"(d[88]), "+f"(d[89]), "+f"(d[90]), "+f"(d[91]), "+f"(d[92]), "+f"(d[93]), "+f"(d[94]), "+f"(d[95])
      : "r"(da), "n"(HA), "r"(db), "n"(HB), "r"(sc));
  }
};

struct FftConst {
  uint32_t f[2][4], fi[4][4];
  float ta[4], tb[4];
};
__device__ __forceinline__ void cis(int m, float scale, float& c, float& s) {
  const float a = (float)m * (-6.283185307179586f * scale);
  c = __cosf(a);
  s = __sinf(a);
}
__device__ __forceinline__ void fft_tables(uint32_t (&v)[12], int tw) {
  const int row = tw >> 2, ch = tw & 3;
#pragma unroll
  for (int i = 0; i < 4; i++) {
    float c[2], s[2], x[2];
#pragma unroll
    for (int e = 0; e < 2; e++) {
      cis((((32 * (8 * ch + 2 * i + e) + 15) * (4 * row - 63) + 2048) & 4095) - 2048, 1.f / 4096, c[e], s[e]);
      float gc, gs;
      cis((((row & 15) * (8 * (ch & 1) + 2 * i + e) + 8) & 15) - 8, 1.f / 16, gc, gs);
      x[e] = (row >> 4) == (ch >> 1) ? gc : (ch >> 1) ? gs : -gs;
    }
    v[i] = pack2(c[0] * 0.125f, c[1] * 0.125f);
    v[4 + i] = pack2(s[0] * 0.125f, s[1] * 0.125f);
    v[8 + i] = pack2(x[0], x[1]);
  }
#pragma unroll
  for (int i = 0; i < 12; i++) asm volatile("" : "+r"(v[i]));
}
__device__ __forceinline__ void fft_tables_store(const uint32_t (&v)[12], uint32_t sb, int tw) {
  const int row = tw >> 2;
  const uint32_t x = ((tw ^ (row >> 1)) & 3) << 4, a = sb + OFF_FT + (16 * (row >> 3) + (row & 7)) * 64 + x;
  sts128(a, v[0], v[1], v[2], v[3]);
  sts128(a + 512, v[4], v[5], v[6], v[7]);
  sts128(sb + OFF_GT + row * 64 + x, v[8], v[9], v[10], v[11]);
}
__device__ __forceinline__ void fft_twiddles(float (&v)[4], int tw) {
#pragma unroll
  for (int i = 0; i < 2; i++) {
    float c, s;
    cis((2 * (2 * (tw & 3) + i) - 15) * (4 * (tw >> 2) - 63), 1.f / 4096, c, s);
    v[2 * i] = __fdividef(-s, 1.f + c);
    v[2 * i + 1] = s;
  }
  pin<4>(v);
}
__device__ __forceinline__ void fft_matrices(FftConst& k, uint32_t sb, int w, int lane) {
  const uint32_t x = (lane >> 1) & 3;
  const uint4 t0 = lds128(sb + OFF_TT + 512 * w + 16 * lane), t1 = lds128(sb + OFF_TT + 512 * w + 16 * (lane ^ 3));
  k.ta[0] = __uint_as_float(t0.x); k.tb[0] = __uint_as_float(t0.y); k.ta[1] = __uint_as_float(t0.z); k.tb[1] = __uint_as_float(t0.w);
  k.ta[3] = __uint_as_float(t1.x); k.tb[3] = __uint_as_float(t1.y); k.ta[2] = __uint_as_float(t1.z); k.tb[2] = __uint_as_float(t1.w);
#pragma unroll
  for (int i = 0; i < 2; i++) {
    ldsm4(k.f[i], sb + OFF_FT + (16 * w + (lane & 15)) * 64 + (((2 * i + (lane >> 4)) ^ x) << 4));
    ldsm4t(k.fi[i], sb + OFF_FT + (32 * i + lane) * 64 + ((w ^ x) << 4));
#pragma unroll
    for (int j = 0; j < 4; j++) {
      k.fi[2 + i][j] = (j & 1) ? k.fi[i][j - 1] ^ 0x80008000u : k.fi[i][j + 1];
      asm volatile("" : "+r"(k.fi[2 + i][j]));
    }
  }
}
__device__ __forceinline__ void rot(bool inv, float& x, float& y, float a, float b) {
  x = fmaf(inv ? -a : a, y, x);
  y = fmaf(inv ? -b : b, x, y);
  x = fmaf(inv ? -a : a, y, x);
}
__device__ __forceinline__ void twiddle_fwd(uint32_t (&a)[4][4], float* d, const FftConst& k) {
#pragma unroll
  for (int q = 0; q < 4; q++)
#pragma unroll
    for (int j = 0; j < 2; j++) {
      float* x = d + 8 * q + 4 * j;
      rot(j, x[0], x[2], k.ta[2 * j], k.tb[2 * j]);
      rot(j, x[1], x[3], k.ta[2 * j + 1], k.tb[2 * j + 1]);
      a[q & 2][2 * j + (q & 1)] = pack2(x[0], x[1]);
      a[(q & 2) + 1][2 * j + (q & 1)] = pack2(x[2], x[3]);
    }
}
__device__ __forceinline__ void g_step(float* d, const uint32_t (&a)[4][4], uint32_t dre, uint32_t dim) {
  WgRS<32>::set<HI_SW64>(d, a[0], dre);
  WgRS<32>::set<HI_SW64>(d + 16, a[2], dre);
  WgRS<32>::mma<HI_SW64>(d, a[1], dim);
  WgRS<32>::mma<HI_SW64>(d + 16, a[3], dim);
  wg_commit();
}

__device__ __forceinline__ void filter_spectrum(const FftConst& k, uint32_t sb, int c, int wg, int w, int lane) {
  const uint32_t hb = sb + off_ch(c) + U_BYTES, dh = desc_lo(hb, 1024), dg = desc_lo(sb + OFF_GT, 16);
  float H[32];
  uint32_t a[4][4];
  const float dv = __uint_as_float(lds32(sb + OFF_D + 4 * c));
  wg_fence();
  WgRS<64>::set<HI_SW32>(H, k.f[0], dh);
  WgRS<64>::mma<HI_SW32>(H, k.f[1], dh + 32);
  wg_commit();
  wg_wait<0>();
  pin<32>(H);
  twiddle_fwd(a, H, k);
  wg_fence();
  g_step(H, a, dg, dg + 64);
  wg_sync(1 + wg);
  wg_wait<0>();
  pin<32>(H);
#pragma unroll
  for (int j = 0; j < 4; j++) H[4 * (j >> 1) + (j & 1)] += dv;
#pragma unroll
  for (int j = 0; j < 4; j++)
    sts128(hb + 1024 * w + 16 * lane + 512 * (j & 1) + 4096 * (j >> 1), pack2(H[8 * j], H[8 * j + 1]), pack2(H[8 * j + 2], H[8 * j + 3]),
           pack2(H[8 * j + 4], H[8 * j + 5]), pack2(H[8 * j + 6], H[8 * j + 7]));
  __syncwarp();
  if (lane == 0) mbar_arrive(sb + OFF_BAR + 8 * (B_H + c));
  TSM(w == 0, 94 + c);
}

__device__ __forceinline__ void conv_channel(const FftConst& k, uint32_t sb, int c, int wg, int w, int lane) {
  const uint32_t cb = sb + off_ch(c), bars = sb + OFF_BAR;
  const uint32_t du = desc_lo(cb, 1024), dg = desc_lo(sb + OFF_GT, 16), dz = desc_lo(cb + U_BYTES, 16);
  float U[32], H[32];
  uint32_t a[4][4], e[4][4];
  if (ATT_GATE) mbar_wait(bars + 8 * B_ATTN, 0);
  mbar_wait(bars + 8 * (B_U + (c < 3 ? c : 3)), 0);
  TSM(w == 0 && c < 3, 7 + wg);
  wg_fence();
  WgRS<64>::set<HI_SW32>(U, k.f[0], du);
  WgRS<64>::mma<HI_SW32>(U, k.f[1], du + 32);
  wg_commit();
  wg_wait<0>();
  pin<32>(U);
  twiddle_fwd(e, U, k);
  wg_fence();
  g_step(U, e, dg, dg + 64);
  mbar_wait(bars + 8 * (B_H + c), 0);
  uint4 hp[4];
#pragma unroll
  for (int j = 0; j < 4; j++) hp[j] = lds128(cb + U_BYTES + 1024 * w + 16 * lane + 512 * (j & 1) + 4096 * (j >> 1));
#pragma unroll
  for (int j = 0; j < 4; j++) {
    H[8 * j] = bf_lo(hp[j].x); H[8 * j + 1] = bf_hi(hp[j].x); H[8 * j + 2] = bf_lo(hp[j].y); H[8 * j + 3] = bf_hi(hp[j].y);
    H[8 * j + 4] = bf_lo(hp[j].z); H[8 * j + 5] = bf_hi(hp[j].z); H[8 * j + 6] = bf_lo(hp[j].w); H[8 * j + 7] = bf_hi(hp[j].w);
  }
  pin<32>(H);
  wg_wait<0>();
  pin<32>(U);
#pragma unroll
  for (int j = 0; j < 2; j++) {
    float pr[4][2], pi[4][2];
#pragma unroll
    for (int x = 0; x < 2; x++) {
#pragma unroll
      for (int m = 0; m < 4; m++) {
#pragma unroll
        for (int q = 0; q <= m; q++) {
          const int ih = 16 * (q >> 1) + 2 * (q & 1) + 4 * j + x, iu = 16 * ((m - q) >> 1) + 2 * ((m - q) & 1) + 4 * j + x;
          pr[m][x] = q ? fmaf(H[ih], U[iu], pr[m][x]) : H[ih] * U[iu];
          pi[m][x] = q ? fmaf(H[ih], U[iu + 8], pi[m][x]) : H[ih] * U[iu + 8];
          pr[m][x] = fmaf(-H[ih + 8], U[iu + 8], pr[m][x]);
          pi[m][x] = fmaf(H[ih + 8], U[iu], pi[m][x]);
        }
      }
    }
#pragma unroll
    for (int m = 0; m < 4; m++) {
      a[m & 2][2 * j + (m & 1)] = pack2(pr[m][0], pr[m][1]);
      a[(m & 2) + 1][2 * j + (m & 1)] = pack2(pi[m][0], pi[m][1]);
    }
  }
  wg_fence();
  g_step(U, a, dg + 64, dg);
  const uint32_t za = cb + U_BYTES + (8 * w + (lane & 7)) * 128 + (((lane >> 3) ^ (lane & 7)) << 4);
  const uint32_t ya = cb + (lane >> 4) * 1024 + (8 * w + (lane & 7)) * 32 + ((((lane >> 3) ^ (lane >> 2)) & 1) << 4);
  wg_wait<0>();
  pin<32>(U);
  TSIF(w == 0, 80 + c);
#pragma unroll
  for (int p = 0; p < 2; p++) {
#pragma unroll
    for (int i = 0; i < 4; i++) {
      const int j = i & 1;
      float* x = U + 16 * p + 4 * j + (i & 2);
      rot(!j, x[8], x[0], k.ta[2 * j], k.tb[2 * j]);
      rot(!j, x[9], x[1], k.ta[2 * j + 1], k.tb[2 * j + 1]);
      e[p][i] = pack2(x[8], x[9]);
      e[2 + p][i] = pack2(x[0], x[1]);
    }
    stsm4(za ^ (64 * p), e[p]);
    stsm4((za ^ (64 * p)) + 4096, e[2 + p]);
  }
  fence_async_smem();
  wg_sync(1 + wg);
  wg_fence();
  WgRS<64>::set<HI_SW128>(H, k.fi[0], dz);
#pragma unroll
  for (int ks = 1; ks < 4; ks++) WgRS<64>::mma<HI_SW128>(H, k.fi[ks], dz + 128 * ks);
  wg_commit();
  wg_wait<0>();
  pin<32>(H);
  TSIF(w == 0, 88 + c);
#pragma unroll
  for (int j = 0; j < 8; j++)
    a[j >> 2][j & 3] = j < 2 ? pack2(H[4 * j], H[4 * j + 1]) : pack2(H[4 * j] + H[4 * j - 6], H[4 * j + 1] + H[4 * j - 5]);
  stsm4(ya, a[0]);
  stsm4(ya + 2048, a[1]);
  fence_async_smem();
  __syncwarp();
}

__device__ __forceinline__ void prep_slab(uint4* res, const uint2* sw, uint32_t sb, int slab, int w, int lane) {
  const int t = lane & 3, tp = (lane & 7) >> 1, pos = 8 * tp + 2 * (((lane >> 3) + tp) & 3) + (lane & 1);
  const uint32_t base = sb + OFF_KVS + slab * KVS_BYTES + pos * 128;
  uint32_t kk[2][4][4], vv[2][4];
  mbar_wait(sb + OFF_BAR + 8 * (B_KV + slab), 0);
#pragma unroll
  for (int h = 0; h < 2; h++) {
#pragma unroll
    for (int j = 0; j < 4; j++) {
      const uint32_t a = base + 128 * j;
      ldsm4t(kk[h][j], a + (((w + 4 * h) ^ ((a >> 7) & 7)) << 4));
    }
    const uint32_t a = base + KVS_V;
    ldsm4t(vv[h], a + (((w + 4 * h) ^ ((a >> 7) & 7)) << 4));
  }
#pragma unroll
  for (int h = 0; h < 2; h++) {
    uint32_t (&k)[4][4] = kk[h];
    uint32_t (&v)[4] = vv[h];
    const uint32_t w0 = __byte_perm(sw[h].x, 0, 0x1010), w1 = __byte_perm(sw[h].x, 0, 0x3232);
    const uint32_t w2 = __byte_perm(sw[h].y, 0, 0x1010), w3 = __byte_perm(sw[h].y, 0, 0x3232);
#pragma unroll
    for (int m = 0; m < 4; m++)
      v[m] = bmul(badd(badd(badd(bmul(k[0][m], w3), bmul(k[1][m], w2)), bmul(k[2][m], w1)), bmul(k[3][m], w0)), v[m]);
    uint32_t a[4];
#pragma unroll
    for (int m = 0; m < 4; m++) a[m] = (t & 1) ? v[(m + 3) & 3] : v[m];
    res[h] = (t & 2) ? make_uint4(a[2], a[3], a[0], a[1]) : make_uint4(a[0], a[1], a[2], a[3]);
  }
}

__device__ __forceinline__ void prep_gate(const Params& p, int b, int w, int lane) {
  uint2 gw[5], x[4][5];
#pragma unroll
  for (int j = 0; j < 5; j++) gw[j] = ldg64(reinterpret_cast<const uint2*>(p.gate_w) + lane + 32 * j);
#pragma unroll
  for (int i = 0; i < 4; i++)
#pragma unroll
    for (int j = 0; j < 5; j++)
      x[i][j] = ldg64(reinterpret_cast<const uint2*>(p.q) + (16 * b + 4 * w + i) * (DIM / 4) + lane + 32 * j);
  float s[4];
#pragma unroll
  for (int i = 0; i < 4; i++) {
    s[i] = 0.f;
#pragma unroll
    for (int j = 0; j < 5; j++) {
      const uint32_t m0 = bmul(x[i][j].x, gw[j].x), m1 = bmul(x[i][j].y, gw[j].y);
      s[i] += (bf_lo(m0) + bf_hi(m0)) + (bf_lo(m1) + bf_hi(m1));
    }
  }
  const bool h = lane & 16, q = lane & 8;
  const float a = (h ? s[2] : s[0]) + __shfl_xor_sync(0xffffffffu, h ? s[0] : s[2], 16);
  const float c = (h ? s[3] : s[1]) + __shfl_xor_sync(0xffffffffu, h ? s[1] : s[3], 16);
  float z = (q ? c : a) + __shfl_xor_sync(0xffffffffu, q ? a : c, 8);
#pragma unroll
  for (int o = 4; o > 0; o >>= 1) z += __shfl_xor_sync(0xffffffffu, z, o);
  z = bf_lo(pack2(z, 0.f));
  if ((lane & 7) == 0) g_gate[16 * b + 4 * w + (lane >> 3)] = bf_lo(pack2(__fdividef(1.f, 1.f + __expf(-z)), 0.f));
}

__device__ __forceinline__ uint32_t bmax(uint32_t a, uint32_t b) {
  uint32_t d;
  asm("max.bf16x2 %0, %1, %2;" : "=r"(d) : "r"(a), "r"(b));
  return d;
}
__device__ __forceinline__ void softmax_two(const float (&l)[2][2], uint32_t& p0, uint32_t& p1) {
  constexpr float kScale = 0.22360679774997896f, kLog2e = 1.4426950408889634f;
  const uint32_t r0 = pack2(l[0][0], l[1][0]), r1 = pack2(l[0][1], l[1][1]);
  const uint32_t x0 = pack2(bf_lo(r0) * kScale, bf_hi(r0) * kScale), x1 = pack2(bf_lo(r1) * kScale, bf_hi(r1) * kScale);
  uint32_t m = bmax(x0, x1);
  m = bmax(m, __shfl_xor_sync(0xffffffffu, m, 1));
  m = bmax(m, __shfl_xor_sync(0xffffffffu, m, 2));
  const float m0 = bf_lo(m) * kLog2e, m1 = bf_hi(m) * kLog2e;
  p0 = pack2(ex2(bf_lo(x0) * kLog2e - m0), ex2(bf_lo(x1) * kLog2e - m0));
  p1 = pack2(ex2(bf_hi(x0) * kLog2e - m1), ex2(bf_hi(x1) * kLog2e - m1));
}

__device__ __forceinline__ void halo_read(uint32_t (&kpv)[10], uint32_t (&vpv)[10], uint32_t (&tg)[7], const uint4* hp) {
#pragma unroll
  for (int j = 0; j < 7; j++) {
    uint32_t x0, x1, x2;
    asm volatile("ld.relaxed.gpu.global.v4.u32 {%0, %1, %2, %3}, [%4];"
                 : "=r"(x0), "=r"(x1), "=r"(x2), "=r"(tg[j]) : "l"(hp + 32 * j) : "memory");
    if (j < 4) kpv[3 * j] = x0; else vpv[3 * j - 10] = x0;
    if (j < 3) kpv[3 * j + 1] = x1; else vpv[3 * j - 9] = x1;
    if (j < 3) kpv[3 * j + 2] = x2; else if (j < 6) vpv[3 * j - 8] = x2;
  }
}

template <int ROT>
__device__ __forceinline__ void pack_qkv(const float* acc, uint32_t (&qlo)[10], uint32_t (&qhi)[10], uint32_t (&klo)[10],
                                         uint32_t (&khi)[10], uint32_t (&vlo)[10], uint32_t (&vhi)[10]) {
#pragma unroll
  for (int j = 0; j < 10; j++) {
    const int x = (j + ROT) % 10, tq = x < 8 ? x : 16 + x, tk = x < 8 ? 8 + x : 18 + x, tv = x < 8 ? 16 + x : 20 + x;
    khi[j] = pack2(acc[4 * tk + 2], acc[4 * tk + 3]);
    vhi[j] = movm(pack2(acc[4 * tv + 2], acc[4 * tv + 3]));
    qlo[j] = pack2(acc[4 * tq], acc[4 * tq + 1]);
    qhi[j] = pack2(acc[4 * tq + 2], acc[4 * tq + 3]);
    klo[j] = pack2(acc[4 * tk], acc[4 * tk + 1]);
    vlo[j] = pack2(acc[4 * tv], acc[4 * tv + 1]);
    asm volatile("" : "+r"(khi[j]), "+r"(qlo[j]), "+r"(qhi[j]), "+r"(klo[j]), "+r"(vlo[j]));
  }
}

template <int ROT> __device__ __forceinline__ void halo_send(const float* acc, uint4* ho, uint32_t tag) {
#pragma unroll
  for (int j = 0; j < 7; j++) {
    uint32_t x[3];
#pragma unroll
    for (int e = 0; e < 3; e++) {
      const int i = 3 * j + e, y = (i % 10 + ROT) % 10, tk = y < 8 ? 8 + y : 18 + y, tv = y < 8 ? 16 + y : 20 + y;
      x[e] = i < 10 ? pack2(acc[4 * tk + 2], acc[4 * tk + 3]) : i < 20 ? movm(pack2(acc[4 * tv + 2], acc[4 * tv + 3])) : 0u;
    }
    asm volatile("st.relaxed.gpu.global.v4.u32 [%0], {%1, %2, %3, %4};" ::"l"(ho + 32 * j), "r"(x[0]), "r"(x[1]), "r"(x[2]), "r"(tag) : "memory");
  }
}

__device__ __forceinline__ void attention(float* acc, uint32_t sb, int b, int par, int w, int lane, uint32_t tag) {
  const int g = lane >> 2, t = lane & 3;
  uint32_t klo[10], khi[10], vlo[10], vhi[10], qlo[10], qhi[10], kpv[10], vpv[10];
  if (HALO_FIRST && w == 3 && b < NCTA - 8) {
    uint4* ho = g_halo + (b * 2 + par) * 224 + lane;
    if (tail_first(b & 7)) halo_send<8>(acc, ho, tag);
    else halo_send<0>(acc, ho, tag);
    TSIF(par == 0, 76);
    pin<120>(acc);
  }
  if (tail_first(b & 7)) pack_qkv<8>(acc, qlo, qhi, klo, khi, vlo, vhi);
  else pack_qkv<0>(acc, qlo, qhi, klo, khi, vlo, vhi);
  const uint32_t xa = sb + OFF_KVX + (par * 3) * 2560 + lane * 16;
  if (w < 3) {
    sts128(xa + w * 2560, khi[0], khi[1], khi[2], khi[3]);
    sts128(xa + w * 2560 + 512, khi[4], khi[5], khi[6], khi[7]);
    sts128(xa + w * 2560 + 1024, khi[8], khi[9], vhi[0], vhi[1]);
    sts128(xa + w * 2560 + 1536, vhi[2], vhi[3], vhi[4], vhi[5]);
    sts128(xa + w * 2560 + 2048, vhi[6], vhi[7], vhi[8], vhi[9]);
  } else if (!HALO_FIRST && b < NCTA - 8) {
    uint4* ho = g_halo + (b * 2 + par) * 224 + lane;
#pragma unroll
    for (int j = 0; j < 7; j++) {
      const uint32_t x0 = j < 4 ? khi[3 * j] : vhi[3 * j - 10], x1 = j < 3 ? khi[3 * j + 1] : vhi[3 * j - 9];
      const uint32_t x2 = j < 3 ? khi[3 * j + 2] : j < 6 ? vhi[3 * j - 8] : 0u;
      asm volatile("st.relaxed.gpu.global.v4.u32 [%0], {%1, %2, %3, %4};" ::"l"(ho + 32 * j), "r"(x0), "r"(x1), "r"(x2), "r"(tag) : "memory");
    }
  }
  TSIF(par == 0 && w == 1, 64);
  TSIF(par == 0 && w == 3 && !HALO_FIRST, 76);
#pragma unroll
  for (int j = 0; j < 10; j++) vlo[j] = movm(vlo[j]);
  const bool far0 = 2 * t > g, far1 = 2 * t + 1 > g;
  const uint32_t mfar = (far0 ? 0x0000FFFFu : 0u) | (far1 ? 0xFFFF0000u : 0u);
  float slo[4][2], shi[4][2], lg[2][2];
  uint32_t phi[4], plo[4], qml[4], qmh[4];
#pragma unroll
  for (int h = 0; h < 4; h++) {
    const int f = h == 0 ? 0 : h == 1 ? 3 : h == 2 ? 5 : 8, hf = h < 2 ? 2 : 7;
    const bool mine = (h & 1) ? t >= 2 : t < 2;
    qml[h] = mine ? qlo[hf] : 0u;
    qmh[h] = mine ? qhi[hf] : 0u;
    float a[4] = {0.f, 0.f, 0.f, 0.f}, c[4] = {0.f, 0.f, 0.f, 0.f};
    mma16816(a, qlo[f], qhi[f], qlo[f + 1], qhi[f + 1], klo[f], klo[f + 1]);
    mma16816(c, qlo[f], qhi[f], qlo[f + 1], qhi[f + 1], khi[f], khi[f + 1]);
    mma1688(a, qml[h], qmh[h], klo[hf]);
    mma1688(c, qml[h], qmh[h], khi[hf]);
    slo[h][0] = a[0];
    slo[h][1] = a[1];
    shi[h][0] = lg[h & 1][0] = far0 ? a[2] : c[2];
    shi[h][1] = lg[h & 1][1] = far1 ? a[3] : c[3];
    if (!ATT_MERGE && (h & 1)) softmax_two(lg, phi[h - 1], phi[h]);
  }
  TSIF(par == 0 && w == 1, 65);
  wg_sync(1 + par);
  TSIF(par == 0 && w == 1, 66);
  const bool nohist = (w == 0) && (b < 8);
  const uint4* hp = g_halo + ((b - 8) * 2 + par) * 224 + lane;
  uint32_t tg[7];
  if (w > 0) {
    const uint4 v0 = lds128(xa + (w - 1) * 2560), v1 = lds128(xa + (w - 1) * 2560 + 512), v2 = lds128(xa + (w - 1) * 2560 + 1024);
    const uint4 v3 = lds128(xa + (w - 1) * 2560 + 1536), v4 = lds128(xa + (w - 1) * 2560 + 2048);
    kpv[0] = v0.x; kpv[1] = v0.y; kpv[2] = v0.z; kpv[3] = v0.w; kpv[4] = v1.x; kpv[5] = v1.y; kpv[6] = v1.z; kpv[7] = v1.w;
    kpv[8] = v2.x; kpv[9] = v2.y; vpv[0] = v2.z; vpv[1] = v2.w; vpv[2] = v3.x; vpv[3] = v3.y; vpv[4] = v3.z; vpv[5] = v3.w;
    vpv[6] = v4.x; vpv[7] = v4.y; vpv[8] = v4.z; vpv[9] = v4.w;
  } else if (nohist) {
#pragma unroll
    for (int j = 0; j < 10; j++) kpv[j] = vpv[j] = 0u;
  } else {
    TSIF(par == 0, 77);
    halo_read(kpv, vpv, tg, hp);
  }
  if (w == 0 && !nohist) {
    int spins = 0;
    while (true) {
      bool ok = true;
#pragma unroll
      for (int j = 0; j < 7; j++) ok = ok && tg[j] == tag;
      if (__all_sync(0xffffffffu, ok) || ++spins > SPIN_LIMIT) break;
      halo_read(kpv, vpv, tg, hp);
    }
    TSIF(par == 0, 79);
  }
#pragma unroll
  for (int h = 0; h < 4; h++) {
    const int f = h == 0 ? 0 : h == 1 ? 3 : h == 2 ? 5 : 8, hf = h < 2 ? 2 : 7;
    float a[4] = {0.f, 0.f, 0.f, 0.f};
    mma16816(a, qlo[f], qhi[f], qlo[f + 1], qhi[f + 1], kpv[f], kpv[f + 1]);
    mma1688(a, qml[h], qmh[h], kpv[hf]);
    const float ninf = __int_as_float(0xff800000);
    lg[h & 1][0] = far0 ? (nohist ? ninf : a[0]) : slo[h][0];
    lg[h & 1][1] = far1 ? (nohist ? ninf : a[1]) : slo[h][1];
    if (h & 1) {
      softmax_two(lg, plo[h - 1], plo[h]);
      if (ATT_MERGE) {
        const float lh[2][2] = {{shi[h - 1][0], shi[h - 1][1]}, {shi[h][0], shi[h][1]}};
        softmax_two(lh, phi[h - 1], phi[h]);
      }
    }
  }
  TSIF(par == 0 && w <= 1, 67 + w);
  uint32_t ov[20];
#pragma unroll
  for (int hp = 0; hp < 2; hp++) {
    const int hf = hp ? 7 : 2;
    float sh[4] = {0.f, 0.f, 0.f, 0.f}, i0 = 0.f, i1 = 0.f;
#pragma unroll
    for (int e = 0; e < 2; e++) {
      const int h = 2 * hp + e, f = h == 0 ? 0 : h == 1 ? 3 : h == 2 ? 5 : 8;
      const uint32_t a0 = plo[h] & mfar, a2 = plo[h] & ~mfar, a3 = phi[h] & mfar, c1 = phi[h] & ~mfar;
      float sum[4] = {0.f, 0.f, 0.f, 0.f};
      mma1688(sum, plo[h], phi[h], 0x3F803F80u);
      const float r0 = rcp(sum[0]), r1 = rcp(sum[2]);
#pragma unroll
      for (int j = f; j < f + 2; j++) {
        float o[4] = {0.f, 0.f, 0.f, 0.f};
        mma16816(o, a0, 0u, a2, a3, vpv[j], vlo[j]);
        mma1688(o, 0u, c1, vhi[j]);
        ov[2 * j] = pack2(o[0] * r0, o[1] * r0);
        ov[2 * j + 1] = pack2(o[2] * r1, o[3] * r1);
      }
      const bool mine = e ? g >= 4 : g < 4;
      mma16816(sh, a0, 0u, a2, a3, mine ? vpv[hf] : 0u, mine ? vlo[hf] : 0u);
      mma1688(sh, 0u, c1, mine ? vhi[hf] : 0u);
      if (e == 0 || t >= 2) {
        i0 = r0;
        i1 = r1;
      }
    }
    ov[2 * hf] = pack2(sh[0] * i0, sh[1] * i0);
    ov[2 * hf + 1] = pack2(sh[2] * i1, sh[3] * i1);
  }
  TS(32 + 4 * par + w);
  mbar_wait(sb + OFF_BAR + 8 * B_P1, 0);
  const uint32_t oa = sb + OFF_OA + (lane >> 4) * 2048 + (32 * w + 2 * (lane & 15) + par) * 16;
#pragma unroll
  for (int j = 0; j < 5; j++) stsm4(oa + 4096 * j, ov + 4 * j);
  TSIF(par == 0 && w == 0, 120);
  fence_async_smem();
  TSIF(par == 0 && w == 0, 121);
  __syncwarp();
  if (lane == 0) mbar_arrive(sb + OFF_BAR + 8 * B_ATTN);
  TSM(w == 0 || w == 2, 122 + par + (w == 2 ? 3 : 0));
}

struct Maps {
  CUtensorMap x, wm, wt, k, v, y, wo, qm, qt, om, ot, u;
};

__device__ __forceinline__ void load_stage(uint32_t sb, int kb, int b, const Maps& m) {
  const uint32_t st = sb + (kb & 3) * STAGE_BYTES, bar = sb + OFF_BAR + 8 * (B_FULL1 + (kb & 3));
  const int r = b >> 3, hg = b & 7, slab = kb - KV_KB;
  const bool kv = slab >= 0 && slab < 5;
  const uint32_t kbar = sb + OFF_BAR + 8 * (B_KV + slab), dst = sb + OFF_KVS + slab * KVS_BYTES;
  mbar_expect_tx(bar, STAGE_BYTES);
  if (kv) mbar_expect_tx(kbar, KVS_BYTES);
  tma_3d(st, &m.x, 64 * kb, 64 * r, 0, bar);
  if (kv && KV_MIX) tma_3d(dst, &m.k, 0, 32 * (b >> 1) - 3, 2 * slab + (b & 1), kbar);
  tma_3d(st + ST_W, &m.wm, 80 * hg + (tail_first(hg) ? 16 : 0), 64 * kb, 0, bar);
  if (kv && KV_MIX) tma_3d(dst + KVS_V, &m.v, 0, 32 * (b >> 1), 2 * slab + (b & 1), kbar);
  tma_3d(st + ST_WT, &m.wt, 80 * hg + (tail_first(hg) ? 0 : 64), 64 * kb, 0, bar);
  if (kv && !KV_MIX) tma_3d(dst, &m.k, 0, 32 * (b >> 1) - 3, 2 * slab + (b & 1), kbar);
  if (kv && !KV_MIX) tma_3d(dst + KVS_V, &m.v, 0, 32 * (b >> 1), 2 * slab + (b & 1), kbar);
}

__global__ void __launch_bounds__(NTHR, 1) fused_kernel(const __grid_constant__ Maps m, const Params p) {
  extern __shared__ __align__(1024) uint8_t smem[];
  const uint32_t sb = (uint32_t)__cvta_generic_to_shared(smem);
  const uint32_t bars = sb + OFF_BAR;
  const int tid = threadIdx.x, lane = tid & 31;
  int b = blockIdx.x;
  if (BMAP == 1) b = (((b & 63) >> 3) * 2 + (b & 1)) * 8 + (((b < 64 ? 0x6521 : 0x7430) >> (4 * ((b >> 1) & 3))) & 7);
  if (BMAP == 2) b = ((b & 63) >> 2) * 8 + (((b < 64 ? 0x6521 : 0x7430) >> (4 * (b & 3))) & 7);
  if (BMAP == 3) b = (((b & 63) >> 3) * 2 + (b & 1)) * 8 + (((b < 64 ? 0x7430 : 0x6521) >> (4 * ((b >> 1) & 3))) & 7);
  if (BMAP == 4) b = (((b >> 4) * 2 + (b & 1)) * 8) + ((b >> 1) & 7);
  if (BMAP == 5) b = 127 - b;
  const int r = b >> 3, hg = b & 7;

  if (tid == T_ISSUE) {
    TSM(true, 0);
#pragma unroll
    for (int i = 0; i < 4; i++) mbar_init(bars + 8 * (B_FULL1 + i), 1);
#pragma unroll
    for (int i = 0; i < 3; i++) mbar_init(bars + 8 * (B_KV + i), 1);
    fence_async_smem();
#pragma unroll 1
    for (int kb = 0; kb <= PRE2; kb++) load_stage(sb, kb, b, m);
  } else if (tid >= T_PF && tid < T_PF + 12) {
    tm_prefetch(&m.x + (tid - T_PF));
  } else if (tid == T_INIT) {
#pragma unroll
    for (int i = 0; i < 4; i++) mbar_init(bars + 8 * (B_EMPTY1 + i), 8);
#pragma unroll
    for (int i = 0; i < 8; i++) mbar_init(bars + 8 * (B_FULL2 + i), 1);
#pragma unroll
    for (int i = 0; i < 4; i++) mbar_init(bars + 8 * (B_EMPTY2 + i), 8);
#pragma unroll
    for (int i = 0; i < 4; i++) mbar_init(bars + 8 * (B_U + i), 1);
    mbar_init(bars + 8 * B_HA, 4);
    mbar_init(bars + 8 * B_GATE, 4);
    mbar_init(bars + 8 * B_HB, 1);
    mbar_init(bars + 8 * B_KVD, 4);
    mbar_init(bars + 8 * B_QF, 1);
    mbar_init(bars + 8 * B_ATTN, 8);
    mbar_init(bars + 8 * B_P1, 8);
    mbar_init(bars + 8 * B_C34, 1);
#pragma unroll
    for (int i = 0; i < 5; i++) mbar_init(bars + 8 * (B_YST + i), 4);
#pragma unroll
    for (int i = 0; i < 5; i++) mbar_init(bars + 8 * (B_US + i), 4);
    mbar_init(bars + 8 * B_YSIG, 1);
    mbar_init(bars + 8 * B_YFULL, 1);
    mbar_init(bars + 8 * B_EPOCH, 1);
    mbar_init(bars + 8 * B_PREP, 4);
    mbar_init(bars + 8 * B_USIG, 1);
    mbar_init(bars + 8 * B_WST, 1);
#pragma unroll
    for (int i = 3; i < 5; i++) mbar_init(bars + 8 * (B_KV + i), 1);
    mbar_init(bars + 8 * B_E3, 8);
    mbar_init(bars + 8 * B_LAST, 1);
    mbar_init(bars + 8 * B_OSIG, 1);
    mbar_init(bars + 8 * B_WOP, 1);
    fence_async_smem();
  }
  const int warp = __shfl_sync(0xffffffffu, tid >> 5, 0), wg = warp >> 2, w = warp & 3;
  __syncthreads();

  if (wg == 3) {
    asm volatile("setmaxnreg.dec.sync.aligned.u32 56;");
    if (w == 0) {
      if (lane == 0) {
#pragma unroll 1
        for (int kb = 1 + PRE2; kb < 10; kb++) {
          if (kb >= 4 && SLEEP_P1) mbar_sleep(bars + 8 * (kb == 7 ? B_E3 : B_EMPTY1 + (kb & 3)), (kb >> 3) & 1);
          if (kb >= 4 && !SLEEP_P1) mbar_wait(bars + 8 * (kb == 7 ? B_E3 : B_EMPTY1 + (kb & 3)), (kb >> 3) & 1);
          TSIF(kb >= 4, 44 + kb);
          load_stage(sb, kb, b, m);
          TSIF(kb == 3, 60);
          if (kb == TRIG_KB) mbar_arrive(bars + 8 * B_LAST);
        }
        mbar_sleep(bars + 8 * B_WOP, 0);
        mbar_sleep(bars + 8 * WL_TRIG, 0);
        mbar_sleep(bars + 8 * B_EPOCH, 0);
        flag_wait(g_cnt + C_W + 32 * hg, (lds32(sb + OFF_EPOCH) + 1) * 16);
        TS(30);
#pragma unroll 1
        for (int j = 0; j < 8; j++) {
          if (j >= 6) mbar_sleep(bars + 8 * (B_EMPTY2 + j - 6), 0);
          if (j == 4) mbar_sleep(bars + 8 * B_ATTN, 0);
          TSIF(j >= 6, 100 + j);
          if (RF_GATE && j == 6) mbar_sleep(bars + 8 * B_YSIG, 0);
          mbar_expect_tx(bars + 8 * (B_FULL2 + j), j == 0 ? WO_BYTES : j == 5 ? O_BYTES + WO_BYTES + 512 : O_BYTES + WO_BYTES);
          bulk_load(sb + off_w(j), g_WO + (hg * 8 + step_src(hg, j)) * 800, WO_BYTES, bars + 8 * (B_FULL2 + j));
        }
        mbar_sleep(bars + 8 * (B_EMPTY2 + 3), 0);
        mbar_expect_tx(bars + 8 * B_QF, O_BYTES);
        tma_2d(sb + OFF_QS, &m.qm, 80 * hg, 128 * r, bars + 8 * B_QF);
        tma_2d(sb + OFF_QT, &m.qt, 80 * hg + 64, 128 * r, bars + 8 * B_QF);
      }
    } else if (w == 1) {
      unsigned epoch = 0;
      if (lane == 0) {
        epoch = atomicAdd(g_cnt + C_LAUNCH, 1u) / NCTA;
        asm volatile("st.shared.u32 [%0], %1;" ::"r"(sb + OFF_EPOCH), "r"(epoch) : "memory");
        mbar_arrive(bars + 8 * B_EPOCH);
        mbar_sleep(bars + 8 * B_KVD, 0);
        mbar_expect_tx(bars + 8 * B_HB, 5 * 4096);
#pragma unroll 1
        for (int c = 0; c < 5; c++) {
          if (c == 3) mbar_sleep(bars + 8 * B_S3, 0);
          bulk_load(sb + off_ch(c) + U_BYTES, p.ssm_k + (5 * b + c) * SEQ, 4096, bars + 8 * B_HB);
        }
#pragma unroll
        for (int c = 0; c < 4; c++) mbar_expect_tx(bars + 8 * (B_U + c), c < 3 ? U_BYTES : 2 * U_BYTES);
        const uint4* usrc = g_U + 5 * b * U_PITCH;
        mbar_sleep(bars + 8 * B_USIG, 0);
        flag_wait(g_cnt + C_PREP + 32 * (b & 15), (epoch + 1) * NCTA);
        TS(23);
#pragma unroll
        for (int c = 0; c < 5; c++) {
          if (c == 3) mbar_sleep(bars + 8 * (B_U + 2), 0);
          bulk_load(sb + off_ch(c), usrc + c * U_PITCH, U_BYTES, bars + 8 * (B_U + (c < 3 ? c : 3)));
          TSIF(c == 0 || c == 4, 116 + (c >> 2));
        }
      }
      epoch = __shfl_sync(0xffffffffu, epoch, 0);
      if (lane < 8) {
        const int src = (b & ~7) | step_src(hg, lane);
        mbar_sleep(bars + 8 * B_OSIG, 0);
        TS(20);
        flag_wait(g_cnt + C_O + 32 * src, epoch + 1);
        if (lane >= 1 && lane < 4) bulk_load(sb + off_o(lane), g_O + src * 1280, O_BYTES, bars + 8 * (B_FULL2 + lane));
        __syncwarp(0xff);
        TS(21);
        if (lane == 5) bulk_load(sb + OFF_GATE, g_gate + 128 * r, 512, bars + 8 * (B_FULL2 + 5));
#pragma unroll 1
        for (int j = 4; j < 8; j++) {
          if (lane == j) {
            mbar_sleep(bars + 8 * (j < 6 ? B_C34 : B_EMPTY2 + j - 6), 0);
            if (RF_GATE && j == 6) mbar_sleep(bars + 8 * B_YSIG, 0);
            bulk_load(sb + off_o(j), g_O + src * 1280, O_BYTES, bars + 8 * (B_FULL2 + j));
          }
          __syncwarp(0xff);
        }
        TS(22);
      }
    } else if (w == 2) {
      mbar_sleep(bars + 8 * B_PREP, 0);
      flag_signal(g_cnt + C_PREP, 16, lane);
      TS(25);
      if (lane == 0) mbar_arrive(bars + 8 * B_USIG);
      mbar_sleep(bars + 8 * B_GATE, 0);
      if ((NOMB & 1) && lane == 0) asm volatile("fence.release.gpu;" ::: "memory");
      mbar_sleep(bars + 8 * B_ATTN, 0);
      if (lane == 0) {
        if (O_DEFER) mbar_sleep(bars + 8 * (B_U + 3), 0);
        asm volatile("cp.async.bulk.global.shared::cta.bulk_group [%0], [%1], 20480;\ncp.async.bulk.commit_group;\n"
                     "cp.async.bulk.wait_group 0;\nfence.proxy.async.global;" ::"l"(g_O + b * 1280), "r"(sb + OFF_OA) : "memory");
      }
      TS(74);
      if (!(NOMB & 1)) flag_signal(g_cnt + C_O + 32 * b, 1, lane);
      else if (lane == 0) flag_bump(g_cnt + C_O + 32 * b);
      TS(26);
      if (lane == 0) mbar_arrive(bars + 8 * B_OSIG);

    } else {
      if (lane == 0) {
        uint4* dst = g_WO + (hg * 8 + (r >> 1)) * 800 + (r & 1) * 80;
        mbar_sleep(bars + 8 * B_P1, 0);
        mbar_sleep(bars + 8 * WB_TRIG, 0);
        mbar_expect_tx(bars + 8 * B_WST, WO_BYTES / 2);
        tma_3d(sb + OFF_WS, &m.wo, 0, 40 * r, 5 * hg, bars + 8 * B_WST);
        mbar_sleep(bars + 8 * B_WST, 0);
        mbar_sleep(bars + 8 * WO_TRIG, 0);
#pragma unroll 1
        for (int n = 0; n < 5; n++)
          asm volatile("cp.async.bulk.global.shared::cta.bulk_group [%0], [%1], 1280;" ::"l"(dst + 160 * n), "r"(sb + OFF_WS + 1280 * n) : "memory");
        asm volatile("cp.async.bulk.commit_group;\ncp.async.bulk.wait_group 0;\nfence.proxy.async.global;" ::: "memory");
        if (!(NOMB & 4)) asm volatile("fence.release.gpu;" ::: "memory");
        flag_bump(g_cnt + C_W + 32 * hg);
        mbar_arrive(bars + 8 * B_WOP);
        TS(71);
#pragma unroll 1
        for (int c = 0; c < 5; c++) {
          mbar_sleep(bars + 8 * (B_YST + c), 0);
          asm volatile("cp.async.bulk.global.shared::cta.bulk_group [%0], [%1], 4096;\ncp.async.bulk.commit_group;"
                       ::"l"(g_Y + (5 * b + c) * Y_PITCH), "r"(sb + off_ch(c)) : "memory");
          if (c == 2) {
            asm volatile("cp.async.bulk.wait_group.read 0;" ::: "memory");
            mbar_arrive(bars + 8 * B_C34);
          }
        }
        asm volatile("cp.async.bulk.wait_group 0;\nfence.proxy.async.global;" ::: "memory");
        TS(75);
        if (!(NOMB & 2)) asm volatile("fence.release.gpu;" ::: "memory");
        flag_bump(g_cnt + C_Y + 32 * (b >> 4));
        TS(27);
        mbar_arrive(bars + 8 * B_YSIG);
        mbar_expect_tx(bars + 8 * B_YFULL, 20480);
        flag_wait(g_cnt + C_Y + 32 * hg, (lds32(sb + OFF_EPOCH) + 1) * 16);
        TS(24);
        tma_2d(sb + OFF_YT, &m.y, 128 * r, 80 * hg, bars + 8 * B_YFULL);
        tma_2d(sb + OFF_YT + 10240, &m.y, 128 * r + 64, 80 * hg, bars + 8 * B_YFULL);
      }
    }
  } else {
    asm volatile("setmaxnreg.inc.sync.aligned.u32 152;");
    if (wg < 2) {
      float acc[120];
#pragma unroll
      for (int i = 0; i < 120; i++) acc[i] = 0.f;
      const uint32_t da = desc_lo(sb + wg * 8192, 16), db = desc_lo(sb + ST_W, 8192), dc = desc_lo(sb + ST_WT, 2048);
      if (PW1) pin<120>(acc);
      if (PW1 == 2) mbar_wait(bars + 8 * B_FULL1, 0);
#pragma unroll 1
      for (int kb = 0; kb < 10; kb++) {
        mbar_wait(bars + 8 * (B_FULL1 + (kb & 3)), (kb >> 2) & 1);
        const uint32_t so = (kb & 3) * (STAGE_BYTES >> 4);
        wg_fence();
#pragma unroll
        for (int k = 0; k < 4; k++) {
          WgSST<192>::mma<HI_SW128, HI_SW128>(acc, da + so + 2 * k, db + so + 128 * k, 1);
          WgSST<48>::mma<HI_SW128, HI_SW32>(acc + 96, da + so + 2 * k, dc + so + 32 * k, 1);
        }
        wg_commit();
        wg_wait<1>();
        if (kb > 0 && lane == 0) mbar_arrive(bars + 8 * (kb == 4 ? B_E3 : B_EMPTY1 + ((kb - 1) & 3)));
      }
      mbar_wait(bars + 8 * B_EPOCH, 0);
      const uint32_t tag = lds32(sb + OFF_EPOCH) + 1;
      mbar_wait(bars + 8 * B_S3, 0);
      wg_wait<0>();
      pin<120>(acc);
      if (lane == 0) mbar_arrive(bars + 8 * B_P1);
      TSM(w == 0, 3 + wg);
      attention(acc, sb, b, wg, w, lane, tag);
    } else {
      const int tw = tid & 127, chl = 64 * (b & 1) + 8 * w + (lane >> 2);
      uint4* up = g_U + chl * U_PITCH + ((4 * (b >> 1) + (lane & 3)) ^ ((b >> 2) & 1));
      uint2 sw[10];
      uint32_t dv = 0;
      if (lane < 5) dv = __ldg(reinterpret_cast<const unsigned short*>(p.ssm_D) + 5 * b + lane);
#pragma unroll
      for (int i = 0; i < 10; i++) sw[i] = ldg64(reinterpret_cast<const uint2*>(p.shift_k) + chl + 128 * (i >> 1) + 32 * (i & 1));
      uint32_t tab[12];
      float tt[4];
      fft_tables(tab, tw);
      fft_twiddles(tt, tw);
      uint4 res[10];
#pragma unroll
      for (int i = 0; i < 10; i++) res[i] = make_uint4(0, 0, 0, 0);
#pragma unroll 1
      for (int slab = 0; slab < 5; slab++) {
#pragma unroll
        for (int i = 0; i < 8; i++) res[i] = res[i + 2];
        prep_slab(res + 8, sw, sb, slab, w, lane);
        TSIF(w == 0, 99 + 4 * slab);
#pragma unroll
        for (int i = 0; i < 8; i++) sw[i] = sw[i + 2];
      }
      TSIF(w == 0, 28);
      __syncwarp();
      if (lane == 0) mbar_arrive(bars + 8 * B_KVD + ((res[8].x ^ res[9].x) & p.zero));
      mbar_wait(bars + 8 * B_KVD, 0);
      fft_tables_store(tab, sb, tw);
      mbar_wait(bars + 8 * B_LAST, 0);
#pragma unroll
      for (int i = 0; i < 10; i++) up[(128 * (i >> 1) + 32 * (i & 1)) * U_PITCH] = res[i];
      __syncwarp();
      if (lane == 0) mbar_arrive(bars + 8 * B_PREP);
      TSIF(w == 0 && !U_TMA, 5);
      mbar_wait(bars + 8 * (G_AFTER ? B_USIG : B_LAST), 0);
      prep_gate(p, b, w, lane);
      __syncwarp();
      if (lane == 0) mbar_arrive(bars + 8 * B_GATE);
      TSIF(w == 0, 72);
      mbar_wait(bars + 8 * B_HB, 0);
      TSIF(w == 0, 2);
      const uint32_t ha = sb + U_BYTES + ((tw >> 3) * 16 + 8 + (tw & 7)) * 16;
      uint4 hv[5];
#pragma unroll
      for (int c = 0; c < 5; c++) hv[c] = lds128(ha + off_ch(c));
      __syncwarp();
#pragma unroll
      for (int c = 0; c < 5; c++) sts128((ha ^ 16) + off_ch(c), hv[c].x, hv[c].y, hv[c].z, hv[c].w);
      sts128(sb + OFF_TT + 16 * tw, __float_as_uint(tt[0]), __float_as_uint(tt[1]), __float_as_uint(tt[2]), __float_as_uint(tt[3]));
      if (tw < 5) asm volatile("st.shared.f32 [%0], %1;" ::"r"(sb + OFF_D + 4 * tw), "f"(bf_lo(dv) * 0.125f) : "memory");
      fence_async_smem();
      __syncwarp();
      if (lane == 0) mbar_arrive(bars + 8 * B_HA);
      TSIF(w == 0, 6);
    }

    FftConst fc;
    TSM(w == 0 && wg == 0, 104);
    mbar_wait(bars + 8 * B_HA, 0);
    fft_matrices(fc, sb, w, lane);
    TSM(w == 0 && wg == 0, 105);
    if (ATT_GATE && !H_EARLY) mbar_wait(bars + 8 * B_ATTN, 0);
    TSM(w == 0 && wg == 2, 124);
#pragma unroll 1
    for (uint32_t tasks = wg == 0 ? TASK0 : wg == 1 ? TASK1 : TASK2; tasks; tasks >>= 4) {
      const int c = (tasks & 7) - 1;
      if (!(tasks & 8)) {
        filter_spectrum(fc, sb, c, wg, w, lane);
        continue;
      }
      conv_channel(fc, sb, c, wg, w, lane);
      if (lane == 0) mbar_arrive(bars + 8 * (B_YST + c));
      TSM(w == 0, 10 + c);
    }

    if (wg < 2) {
      const int g = lane >> 2;
      float acc[40];
#pragma unroll
      for (int i = 0; i < 40; i++) acc[i] = 0.f;
      const uint32_t da = desc_lo(sb + wg * 1024, 2048), db = desc_lo(sb, 2560);
      mbar_wait(bars + 8 * B_ATTN, 0);
      mbar_wait(bars + 8 * (B_YST + 3), 0);
      mbar_wait(bars + 8 * (B_YST + 4), 0);
      if (PW2) mbar_wait(bars + 8 * B_FULL2, 0);
      TSM(w == 0, 15 + wg);
#pragma unroll 1
      for (int j = 0; j < 8; j++) {
        mbar_wait(bars + 8 * (B_FULL2 + j), 0);
        const uint32_t oa = da + (off_o(j) >> 4), ob = db + (off_w(j) >> 4);
        wg_fence();
#pragma unroll
        for (int k = 0; k < 5; k++) WgSST<80>::mma<HI_NONE, HI_SW32>(acc, oa + 256 * k, ob + 32 * k, 1);
        wg_commit();
        wg_wait<1>();
        if (j >= 1 && j <= 4 && lane == 0) mbar_arrive(bars + 8 * (B_EMPTY2 + j - 1));
      }
      TSIF(w == 0 && wg == 0, 113);
      const int tr = 64 * wg + 16 * w + (lane & 15);
      const uint32_t fm = sb + OFF_QS + tr * 128, fx = (lane >> 4) ^ (tr & 7);
      const uint32_t ft = sb + OFF_QT + tr * 32 + (((lane >> 4) ^ (tr >> 2)) & 1) * 16;
      const float g0 = __uint_as_float(lds32(sb + OFF_GATE + (64 * wg + 16 * w + g) * 4));
      const float g1 = __uint_as_float(lds32(sb + OFF_GATE + (64 * wg + 16 * w + 8 + g) * 4));
      const uint32_t ga = pack2(g0, g0), gb = pack2(g1, g1);
      const uint32_t na = pack2(1.f - g0, 1.f - g0), nb = pack2(1.f - g1, 1.f - g1);

      wg_wait<0>();
      pin<40>(acc);
      TSM(w == 0, 17 + wg);
      uint32_t pb[20];
#pragma unroll
      for (int j = 0; j < 10; j++) {
        pb[2 * j] = bmul(na, pack2(acc[4 * j], acc[4 * j + 1]));
        pb[2 * j + 1] = bmul(nb, pack2(acc[4 * j + 2], acc[4 * j + 3]));
        asm volatile("" : "+r"(pb[2 * j]), "+r"(pb[2 * j + 1]));
      }
      const uint32_t ya = sb + OFF_YT + wg * 10240 + ((lane >> 4) * 8 + (lane & 7)) * 128 +
                          (((2 * w + (((lane >> 3) & 1) ^ wg)) ^ (lane & 7)) << 4);
      uint32_t qf[20];
      mbar_wait(bars + 8 * B_QF, 0);
#pragma unroll
      for (int j = 0; j < 5; j++) ldsm4(qf + 4 * j, j < 4 ? fm + ((fx ^ (2 * j)) << 4) : ft);
      mbar_wait(bars + 8 * B_YFULL, 0);
      TSM(w == 0 && wg == 0, 19);
#pragma unroll
      for (int j = 0; j < 5; j++) {
        uint32_t y[4];
        ldsm4t(y, ya + 2048 * j);
#pragma unroll
        for (int i = 0; i < 4; i++) qf[4 * j + i] = badd(bmul((i & 1) ? gb : ga, bmul(qf[4 * j + i], y[i])), pb[4 * j + i]);
      }
#pragma unroll
      for (int j = 0; j < 5; j++) stsm4(j < 4 ? fm + ((fx ^ (2 * j)) << 4) : ft, qf + 4 * j);
      fence_async_smem();
      __syncwarp();
      if (lane == 0) {
        const int row = 64 * wg + 16 * w;
        asm volatile("cp.async.bulk.tensor.2d.global.shared::cta.bulk_group [%0, {%2, %3}], [%1];"
                     ::"l"(&m.om), "r"(sb + OFF_QS + row * 128), "r"(80 * hg), "r"(128 * r + row) : "memory");
        asm volatile("cp.async.bulk.tensor.2d.global.shared::cta.bulk_group [%0, {%2, %3}], [%1];"
                     ::"l"(&m.ot), "r"(sb + OFF_QT + row * 32), "r"(80 * hg + 64), "r"(128 * r + row) : "memory");
        asm volatile("cp.async.bulk.commit_group;\ncp.async.bulk.wait_group.read 0;" ::: "memory");
      }
      TSM(true, 40 + 4 * wg + w);
      if (ENDBAR) asm volatile("bar.sync 15, 256;" ::: "memory");
    }
  }
}

typedef CUresult (*EncodeFn)(CUtensorMap*, CUtensorMapDataType, cuuint32_t, void*, const cuuint64_t*, const cuuint64_t*,
                             const cuuint32_t*, const cuuint32_t*, CUtensorMapInterleave, CUtensorMapSwizzle,
                             CUtensorMapL2promotion, CUtensorMapFloatOOBfill);

void encode(EncodeFn fn, CUtensorMap* tm, const void* base, int rank, const cuuint64_t* dims, const cuuint64_t* strides,
            const cuuint32_t* box, CUtensorMapSwizzle swz) {
  const cuuint32_t ones[3] = {1, 1, 1};
  fn(tm, CU_TENSOR_MAP_DATA_TYPE_BFLOAT16, rank, const_cast<void*>(base), dims, strides, box, ones,
     CU_TENSOR_MAP_INTERLEAVE_NONE, swz, CU_TENSOR_MAP_L2_PROMOTION_L2_128B, CU_TENSOR_MAP_FLOAT_OOB_FILL_NONE);
}

}

extern "C" void kernel_launch(void* const* d_in, const int* in_sizes, int n_in, void* d_out, int out_size) {
  (void)in_sizes; (void)n_in; (void)out_size;
  Params p;
  p.q = (const __nv_bfloat16*)d_in[0];
  p.k = (const __nv_bfloat16*)d_in[1];
  p.v = (const __nv_bfloat16*)d_in[2];
  p.shift_k = (const __nv_bfloat16*)d_in[3];
  p.ssm_k = (const __nv_bfloat16*)d_in[4];
  p.ssm_D = (const __nv_bfloat16*)d_in[5];
  p.wqkv = (const __nv_bfloat16*)d_in[7];
  p.wo = (const __nv_bfloat16*)d_in[8];
  p.gate_w = (const __nv_bfloat16*)d_in[9];
  p.out = (__nv_bfloat16*)d_out;
  p.zero = 0;

  static EncodeFn fn = nullptr;
  static void *yaddr = nullptr, *uaddr = nullptr;
  if (!fn) {
    cudaDriverEntryPointQueryResult qr;
    void* f = nullptr;
    cudaGetDriverEntryPoint("cuTensorMapEncodeTiled", &f, cudaEnableDefault, &qr);
    fn = (EncodeFn)f;
    cudaGetSymbolAddress(&yaddr, g_Y);
    cudaGetSymbolAddress(&uaddr, g_U);
    cudaFuncSetAttribute(fused_kernel, cudaFuncAttributeMaxDynamicSharedMemorySize, SMEM_BYTES);
  }
  Maps m;
  {
    const cuuint64_t dims[3] = {640, 1024, 2}, st[2] = {2560, 1280};
    const cuuint32_t box[3] = {64, 64, 2};
    encode(fn, &m.x, p.q, 3, dims, st, box, CU_TENSOR_MAP_SWIZZLE_128B);
  }
  {
    const cuuint64_t dims[3] = {640, 640, 3}, st[2] = {3840, 1280};
    const cuuint32_t box[3] = {64, 64, 3}, boxt[3] = {16, 64, 3};
    encode(fn, &m.wm, p.wqkv, 3, dims, st, box, CU_TENSOR_MAP_SWIZZLE_128B);
    encode(fn, &m.wt, p.wqkv, 3, dims, st, boxt, CU_TENSOR_MAP_SWIZZLE_32B);
  }
  {
    const cuuint64_t dims[3] = {64, 2048, 10}, st[2] = {1280, 128};
    const cuuint32_t boxk[3] = {64, 35, 1}, boxv[3] = {64, 32, 1};
    encode(fn, &m.k, p.k, 3, dims, st, boxk, CU_TENSOR_MAP_SWIZZLE_128B);
    encode(fn, &m.v, p.v, 3, dims, st, boxv, CU_TENSOR_MAP_SWIZZLE_128B);
  }
  {
    const cuuint64_t dims[3] = {16, 640, 40}, st[2] = {1280, 32};
    const cuuint32_t box[3] = {16, 40, 5};
    encode(fn, &m.wo, p.wo, 3, dims, st, box, CU_TENSOR_MAP_SWIZZLE_32B);
  }
  {
    const cuuint64_t dims[2] = {2048, 640}, st[1] = {Y_PITCH * 16};
    const cuuint32_t box[2] = {64, 80};
    encode(fn, &m.y, yaddr, 2, dims, st, box, CU_TENSOR_MAP_SWIZZLE_128B);
    const cuuint64_t stu[1] = {U_PITCH * 16};
    const cuuint32_t boxu[2] = {32, 64};
    encode(fn, &m.u, uaddr, 2, dims, stu, boxu, CU_TENSOR_MAP_SWIZZLE_NONE);
  }
  {
    const cuuint64_t dims[2] = {640, 2048}, st[1] = {1280};
    const cuuint32_t bqm[2] = {64, 128}, bqt[2] = {16, 128}, bom[2] = {64, 16}, bot[2] = {16, 16};
    encode(fn, &m.qm, p.q, 2, dims, st, bqm, CU_TENSOR_MAP_SWIZZLE_128B);
    encode(fn, &m.qt, p.q, 2, dims, st, bqt, CU_TENSOR_MAP_SWIZZLE_32B);
    encode(fn, &m.om, p.out, 2, dims, st, bom, CU_TENSOR_MAP_SWIZZLE_128B);
    encode(fn, &m.ot, p.out, 2, dims, st, bot, CU_TENSOR_MAP_SWIZZLE_32B);
  }
  fused_kernel<<<NCTA, NTHR, SMEM_BYTES>>>(m, p);
}
```

```cpp
#include <cuda.h>
#include <cuda_bf16.h>
#include <cuda_runtime.h>
#include <stdint.h>

namespace {

constexpr int SEQ = 2048, DIM = 640, NCTA = 128, NTHR = 512;

#define TRIG_KB 9
#define KV_KB 2
#define DEV_EXIT 0
#define ATT_GATE 1
#define G_AFTER 0
#define FENCE_LO 0
#define FENCE_HI 0
#define PW1 2
#define PW2 1
#define ENDBAR 0
#define PAD_KB 0
#define Y_ALIAS 1
#define H_EARLY 1
#define NOMB 0
#define SRC_ROT 0
#define WAIT_NS 0
#define WB_TRIG B_USIG
#define G_POS 0
#define TAILF 1
#define T_ISSUE 384
#define T_PF 416
#define T_INIT 448
#define ATT_MERGE 0
#define BMAP 1
#define PRE2 1
#define KV_MIX 0
#define O_DEFER 0
#define TASK0 0x52
#define TASK1 0x3
#define TASK2 0x41
#define HALO_FIRST 1
#define PREV_EARLY 0
#define ACQ 0
#define U_TMA 0
#define U_GATE 0
#define RF_GATE 0
#define WO_TRIG B_WST
#define WL_TRIG B_WOP
#define WO_GATE 1

constexpr uint32_t STAGE_BYTES = 47104, ST_W = 16384, ST_WT = 40960;
constexpr uint32_t O_BYTES = 20480, WO_BYTES = 12800;
constexpr uint32_t OFF_OA = 0;
constexpr uint32_t OFF_QS = 3 * O_BYTES, OFF_QT = OFF_QS + 16384;
constexpr uint32_t OFF_WC = 81920;
constexpr uint32_t OFF_WA = 94720;
constexpr uint32_t OFF_GATE = 145920;
constexpr uint32_t OFF_TT = 146432;
constexpr uint32_t OFF_KVX = 148480;
constexpr uint32_t OFF_CH3 = 163840;
constexpr uint32_t CH_BYTES = 12288, U_BYTES = 4096;
constexpr uint32_t OFF_FT = 225280, OFF_GT = 229376;
constexpr uint32_t OFF_CH0 = 188416;
constexpr uint32_t OFF_KVS = OFF_CH0, KVS_V = 4480, KVS_BYTES = 8576;
constexpr uint32_t OFF_WS = OFF_WA;
__device__ __forceinline__ uint32_t off_us(int s) { return OFF_CH0 + 4096 * ((0x65320 >> (4 * s)) & 7); }
constexpr uint32_t OFF_YT = 163840;
constexpr uint32_t OFF_BAR = 231936;
constexpr uint32_t SMEM_BYTES = OFF_BAR + 512;

enum : uint32_t {
  B_FULL1 = 0, B_EMPTY1 = 4, B_S3 = 7, B_FULL2 = 52, B_EMPTY2 = 13, B_U = 8, B_GATE = 12, B_HA = 19, B_HB = 20,
  B_ATTN = 21, B_C34 = 22, B_CONV = 23, B_YFULL = 24, B_EPOCH = 25, B_PREP = 26, B_P1 = 27, B_LAST = 28,
  B_E3 = 29, B_OSIG = 30, B_WOP = 31, B_USIG = 32, B_WST = 33, B_KV = 34, B_KVD = 39, B_QF = 17, B_YST = 40,
  B_US = 45, B_YSIG = 50
};
constexpr uint32_t OFF_EPOCH = OFF_BAR + 8 * 51, OFF_D = OFF_BAR + 8 * 60;
__device__ __forceinline__ uint32_t off_o(int j) { return j < 4 ? OFF_OA + j * O_BYTES : j < 6 ? OFF_CH0 + (j - 4) * O_BYTES : OFF_OA + (j - 6) * O_BYTES; }
__device__ __forceinline__ uint32_t off_w(int j) { return j < 4 ? OFF_WA + j * WO_BYTES : j == 4 ? OFF_KVX : j == 5 ? OFF_WC : OFF_WA + (j - 6) * WO_BYTES; }
__device__ __forceinline__ int step_src(int hg, int j) { return SRC_ROT ? (hg + j) & 7 : j == 0 ? hg : j <= hg ? j - 1 : j; }
__device__ __forceinline__ bool tail_first(int hg) { return TAILF && (hg & 3) == 3; }
__device__ __forceinline__ uint32_t off_ch(int c) { return (c < 3 ? OFF_CH0 : OFF_CH3 - 3 * CH_BYTES) + c * CH_BYTES; }

#define U_PITCH 264
__device__ __align__(1024) uint4 g_U[DIM * U_PITCH];
__device__ uint4 g_O[NCTA * 1280];
#define g_Y g_U
constexpr int Y_PITCH = U_PITCH;
__device__ uint4 g_WO[64 * 800];
__device__ uint4 g_halo[NCTA * 2 * 7 * 32];
__device__ float g_gate[SEQ + PAD_KB * 256];
__device__ unsigned g_cnt[32 * (1 + 2 * 16 + 8 + NCTA)];
constexpr int C_LAUNCH = 0, C_PREP = 32, C_Y = 32 * 17, C_W = 32 * 33, C_O = 32 * 41;

#define TSM(cond, slot) do { } while (0)
#define TSIF(cond, slot) do { if (__LINE__ >= FENCE_LO && __LINE__ < FENCE_HI) sched_fence(); } while (0)
__device__ __forceinline__ void sched_fence() {
  asm volatile("{\n.reg .pred p;\n.reg .u32 c;\nmov.u32 c, %%clock;\nsetp.eq.u32 p, c, 0;\n@p st.shared.u32 [%0], c;\n}"
               ::"r"(1024 + OFF_EPOCH + 4) : "memory");
}
#define TS(slot) TSIF(true, slot)

struct Params {
  const __nv_bfloat16 *q, *k, *v, *shift_k, *ssm_k, *ssm_D, *wqkv, *wo, *gate_w;
  __nv_bfloat16* out;
  uint32_t zero;
};

#define POLL_NS 0
constexpr int SPIN_LIMIT = 1 << 17;

__device__ __forceinline__ void mbar_init(uint32_t bar, uint32_t count) {
  asm volatile("mbarrier.init.shared::cta.b64 [%0], %1;" ::"r"(bar), "r"(count) : "memory");
}
__device__ __forceinline__ void mbar_expect_tx(uint32_t bar, uint32_t bytes) {
  asm volatile("mbarrier.arrive.expect_tx.shared::cta.b64 _, [%0], %1;" ::"r"(bar), "r"(bytes) : "memory");
}
__device__ __forceinline__ void mbar_arrive(uint32_t bar) {
  asm volatile("mbarrier.arrive.shared::cta.b64 _, [%0];" ::"r"(bar) : "memory");
}
__device__ __forceinline__ void mbar_wait(uint32_t bar, uint32_t parity) {
  uint32_t ok;
  int spins = 0;
  do {
    if (WAIT_NS)
      asm volatile("{\n.reg .pred p;\nmbarrier.try_wait.parity.shared::cta.b64 p, [%1], %2, %3;\nselp.b32 %0, 1, 0, p;\n}"
                   : "=r"(ok) : "r"(bar), "r"(parity), "r"(WAIT_NS) : "memory");
    else
      asm volatile("{\n.reg .pred p;\nmbarrier.try_wait.parity.shared::cta.b64 p, [%1], %2;\nselp.b32 %0, 1, 0, p;\n}"
                   : "=r"(ok) : "r"(bar), "r"(parity) : "memory");
    if (++spins > SPIN_LIMIT) break;
  } while (!ok);
}
__device__ __forceinline__ unsigned flag_read(const unsigned* p) {
  unsigned v;
  asm volatile("ld.relaxed.gpu.global.u32 %0, [%1];" : "=r"(v) : "l"(p) : "memory");
  return v;
}
__device__ __forceinline__ void flag_poll(const unsigned* p, unsigned target) {
  unsigned v;
  int spins = 0;
  do {
    if (POLL_NS && spins) __nanosleep(POLL_NS);
    asm volatile("ld.relaxed.gpu.global.u32 %0, [%1];" : "=r"(v) : "l"(p) : "memory");
    if (++spins > SPIN_LIMIT) break;
  } while ((int)(v - target) < 0);
}
__device__ __forceinline__ void flag_wait(const unsigned* p, unsigned target) {
  flag_poll(p, target);
  if (ACQ) asm volatile("fence.acquire.gpu;\nfence.proxy.async.global;" ::: "memory");
}
__device__ __forceinline__ void flag_signal(unsigned* p, int n, int lane) {
  if (lane == 0) asm volatile("fence.release.gpu;" ::: "memory");
  __syncwarp();
  if (lane < n) asm volatile("red.relaxed.gpu.global.add.u32 [%0], 1;" ::"l"(p + 32 * lane) : "memory");
}
__device__ __forceinline__ void flag_bump(unsigned* p) {
  asm volatile("red.relaxed.gpu.global.add.u32 [%0], 1;" ::"l"(p) : "memory");
}
__device__ __forceinline__ void fence_async_smem() { asm volatile("fence.proxy.async.shared::cta;" ::: "memory"); }
__device__ __forceinline__ void wg_sync(int id) { asm volatile("bar.sync %0, 128;" ::"r"(id) : "memory"); }

__device__ __forceinline__ void tma_2d(uint32_t dst, const CUtensorMap* tm, int c0, int c1, uint32_t bar) {
  asm volatile("cp.async.bulk.tensor.2d.shared::cluster.global.mbarrier::complete_tx::bytes [%0], [%1, {%3, %4}], [%2];"
               ::"r"(dst), "l"(tm), "r"(bar), "r"(c0), "r"(c1) : "memory");
}
__device__ __forceinline__ void tma_3d(uint32_t dst, const CUtensorMap* tm, int c0, int c1, int c2, uint32_t bar) {
  asm volatile("cp.async.bulk.tensor.3d.shared::cluster.global.mbarrier::complete_tx::bytes [%0], [%1, {%3, %4, %5}], [%2];"
               ::"r"(dst), "l"(tm), "r"(bar), "r"(c0), "r"(c1), "r"(c2) : "memory");
}
__device__ __forceinline__ void bulk_load(uint32_t dst, const void* src, uint32_t bytes, uint32_t bar) {
  asm volatile("cp.async.bulk.shared::cluster.global.mbarrier::complete_tx::bytes [%0], [%1], %2, [%3];"
               ::"r"(dst), "l"(src), "r"(bytes), "r"(bar) : "memory");
}
__device__ __forceinline__ void tm_prefetch(const CUtensorMap* tm) {
  asm volatile("prefetch.tensormap [%0];" ::"l"(tm) : "memory");
}

__device__ __forceinline__ void wg_fence() { asm volatile("wgmma.fence.sync.aligned;" ::: "memory"); }
__device__ __forceinline__ void wg_commit() { asm volatile("wgmma.commit_group.sync.aligned;" ::: "memory"); }
template <int N> __device__ __forceinline__ void wg_wait() { asm volatile("wgmma.wait_group.sync.aligned %0;" ::"n"(N) : "memory"); }
__device__ __forceinline__ uint32_t desc_lo(uint32_t addr, uint32_t lbo) { return ((addr & 0x3FFFF) >> 4) | ((lbo >> 4) << 16); }
constexpr uint32_t desc_hi(uint32_t sbo, uint32_t swz) { return (sbo >> 4) | (swz << 30); }
constexpr uint32_t HI_SW128 = desc_hi(1024, 1), HI_SW64 = desc_hi(512, 2), HI_SW32 = desc_hi(256, 3), HI_NONE = desc_hi(128, 0);
template <int N> __device__ __forceinline__ void pin(float* d) {
#pragma unroll
  for (int i = 0; i < N; i++) asm volatile("" : "+f"(d[i])::"memory");
}

__device__ __forceinline__ uint32_t lds32(uint32_t a) {
  uint32_t v;
  asm volatile("ld.volatile.shared.u32 %0, [%1];" : "=r"(v) : "r"(a) : "memory");
  return v;
}
__device__ __forceinline__ uint4 ldg128(const void* a) {
  uint4 v;
  asm volatile("ld.global.nc.v4.u32 {%0, %1, %2, %3}, [%4];" : "=r"(v.x), "=r"(v.y), "=r"(v.z), "=r"(v.w) : "l"(a) : "memory");
  return v;
}
__device__ __forceinline__ uint2 ldg64(const void* a) {
  uint2 v;
  asm volatile("ld.global.nc.v2.u32 {%0, %1}, [%2];" : "=r"(v.x), "=r"(v.y) : "l"(a) : "memory");
  return v;
}
__device__ __forceinline__ void ldsm4(uint32_t* r, uint32_t a) {
  asm volatile("ldmatrix.sync.aligned.m8n8.x4.shared.b16 {%0, %1, %2, %3}, [%4];"
               : "=r"(r[0]), "=r"(r[1]), "=r"(r[2]), "=r"(r[3]) : "r"(a) : "memory");
}
__device__ __forceinline__ void ldsm4t(uint32_t* r, uint32_t a) {
  asm volatile("ldmatrix.sync.aligned.m8n8.x4.trans.shared.b16 {%0, %1, %2, %3}, [%4];"
               : "=r"(r[0]), "=r"(r[1]), "=r"(r[2]), "=r"(r[3]) : "r"(a) : "memory");
}
__device__ __forceinline__ uint4 lds128(uint32_t a) {
  uint4 v;
  asm volatile("ld.shared.v4.u32 {%0, %1, %2, %3}, [%4];" : "=r"(v.x), "=r"(v.y), "=r"(v.z), "=r"(v.w) : "r"(a) : "memory");
  return v;
}
__device__ __forceinline__ void sts128(uint32_t a, uint32_t x, uint32_t y, uint32_t z, uint32_t w) {
  asm volatile("st.shared.v4.u32 [%0], {%1, %2, %3, %4};" ::"r"(a), "r"(x), "r"(y), "r"(z), "r"(w) : "memory");
}
__device__ __forceinline__ void stsm4(uint32_t a, const uint32_t* r) {
  asm volatile("stmatrix.sync.aligned.m8n8.x4.shared.b16 [%0], {%1, %2, %3, %4};" ::"r"(a), "r"(r[0]), "r"(r[1]), "r"(r[2]), "r"(r[3]) : "memory");
}
__device__ __forceinline__ void stsm4t(uint32_t a, const uint32_t* r) {
  asm volatile("stmatrix.sync.aligned.m8n8.x4.trans.shared.b16 [%0], {%1, %2, %3, %4};" ::"r"(a), "r"(r[0]), "r"(r[1]), "r"(r[2]), "r"(r[3]) : "memory");
}
__device__ __forceinline__ uint32_t pack2(float lo, float hi) {
  uint32_t r;
  asm("cvt.rn.bf16x2.f32 %0, %1, %2;" : "=r"(r) : "f"(hi), "f"(lo));
  return r;
}
__device__ __forceinline__ uint32_t movm(uint32_t a) {
  uint32_t d;
  asm volatile("movmatrix.sync.aligned.m8n8.trans.b16 %0, %1;" : "=r"(d) : "r"(a));
  return d;
}
__device__ __forceinline__ uint32_t bmul(uint32_t a, uint32_t b) {
  uint32_t d;
  asm("mul.rn.bf16x2 %0, %1, %2;" : "=r"(d) : "r"(a), "r"(b));
  return d;
}
__device__ __forceinline__ uint32_t badd(uint32_t a, uint32_t b) {
  uint32_t d;
  asm("add.rn.bf16x2 %0, %1, %2;" : "=r"(d) : "r"(a), "r"(b));
  return d;
}
__device__ __forceinline__ float bf_lo(uint32_t x) { return __uint_as_float(x << 16); }
__device__ __forceinline__ float bf_hi(uint32_t x) { return __uint_as_float(x & 0xFFFF0000u); }
__device__ __forceinline__ float ex2(float x) {
  float y;
  asm("ex2.approx.ftz.f32 %0, %1;" : "=f"(y) : "f"(x));
  return y;
}
__device__ __forceinline__ float rcp(float x) {
  float y;
  asm("rcp.approx.ftz.f32 %0, %1;" : "=f"(y) : "f"(x));
  return y;
}
__device__ __forceinline__ void mma16816(float* d, uint32_t a0, uint32_t a1, uint32_t a2, uint32_t a3, uint32_t b0, uint32_t b1) {
  asm volatile("mma.sync.aligned.m16n8k16.row.col.f32.bf16.bf16.f32 {%0, %1, %2, %3}, {%4, %5, %6, %7}, {%8, %9}, {%0, %1, %2, %3};"
               : "+f"(d[0]), "+f"(d[1]), "+f"(d[2]), "+f"(d[3])
               : "r"(a0), "r"(a1), "r"(a2), "r"(a3), "r"(b0), "r"(b1));
}
__device__ __forceinline__ void mma1688(float* d, uint32_t a0, uint32_t a1, uint32_t b0) {
  asm volatile("mma.sync.aligned.m16n8k8.row.col.f32.bf16.bf16.f32 {%0, %1, %2, %3}, {%4, %5}, {%6}, {%0, %1, %2, %3};"
               : "+f"(d[0]), "+f"(d[1]), "+f"(d[2]), "+f"(d[3])
               : "r"(a0), "r"(a1), "r"(b0));
}

template <int N> struct WgRS;
template <int N> struct WgSST;
template <> struct WgRS<32> {
  template <uint32_t HB>
  static __device__ __forceinline__ void mma(float* d, const uint32_t* a, uint32_t db) {
    asm volatile("{\n.reg .pred p;\n.reg .b64 db;\nsetp.ne.b32 p, %22, 0;\n"
      "mov.b64 db, {%20, %21};\n"
      "wgmma.mma_async.sync.aligned.m64n32k16.f32.bf16.bf16 {"
      "%0, %1, %2, %3, %4, %5, %6, %7, %8, %9, %10, %11, %12, %13, %14, %15"
      "}, {%16, %17, %18, %19}, db, p, 1, 1, 1;\n}\n"
      : "+f"(d[0]), "+f"(d[1]), "+f"(d[2]), "+f"(d[3]), "+f"(d[4]), "+f"(d[5]), "+f"(d[6]), "+f"(d[7]),
        "+f"(d[8]), "+f"(d[9]), "+f"(d[10]), "+f"(d[11]), "+f"(d[12]), "+f"(d[13]), "+f"(d[14]), "+f"(d[15])
      : "r"(a[0]), "r"(a[1]), "r"(a[2]), "r"(a[3]), "r"(db), "n"(HB), "n"(1));
  }
  template <uint32_t HB>
  static __device__ __forceinline__ void set(float* d, const uint32_t* a, uint32_t db) {
    asm volatile("{\n.reg .pred p;\n.reg .b64 db;\nsetp.ne.b32 p, %22, 0;\n"
      "mov.b64 db, {%20, %21};\n"
      "wgmma.mma_async.sync.aligned.m64n32k16.f32.bf16.bf16 {"
      "%0, %1, %2, %3, %4, %5, %6, %7, %8, %9, %10, %11, %12, %13, %14, %15"
      "}, {%16, %17, %18, %19}, db, p, 1, 1, 1;\n}\n"
      : "=f"(d[0]), "=f"(d[1]), "=f"(d[2]), "=f"(d[3]), "=f"(d[4]), "=f"(d[5]), "=f"(d[6]), "=f"(d[7]),
        "=f"(d[8]), "=f"(d[9]), "=f"(d[10]), "=f"(d[11]), "=f"(d[12]), "=f"(d[13]), "=f"(d[14]), "=f"(d[15])
      : "r"(a[0]), "r"(a[1]), "r"(a[2]), "r"(a[3]), "r"(db), "n"(HB), "n"(0));
  }
};
template <> struct WgRS<64> {
  template <uint32_t HB>
  static __device__ __forceinline__ void mma(float* d, const uint32_t* a, uint32_t db) {
    asm volatile("{\n.reg .pred p;\n.reg .b64 db;\nsetp.ne.b32 p, %38, 0;\n"
      "mov.b64 db, {%36, %37};\n"
      "wgmma.mma_async.sync.aligned.m64n64k16.f32.bf16.bf16 {"
      "%0, %1, %2, %3, %4, %5, %6, %7, %8, %9, %10, %11, %12, %13, %14, %15, "
      "%16, %17, %18, %19, %20, %21, %22, %23, %24, %25, %26, %27, %28, %29, %30, %31"
      "}, {%32, %33, %34, %35}, db, p, 1, 1, 1;\n}\n"
      : "+f"(d[0]), "+f"(d[1]), "+f"(d[2]), "+f"(d[3]), "+f"(d[4]), "+f"(d[5]), "+f"(d[6]), "+f"(d[7]),
        "+f"(d[8]), "+f"(d[9]), "+f"(d[10]), "+f"(d[11]), "+f"(d[12]), "+f"(d[13]), "+f"(d[14]), "+f"(d[15]),
        "+f"(d[16]), "+f"(d[17]), "+f"(d[18]), "+f"(d[19]), "+f"(d[20]), "+f"(d[21]), "+f"(d[22]), "+f"(d[23]),
        "+f"(d[24]), "+f"(d[25]), "+f"(d[26]), "+f"(d[27]), "+f"(d[28]), "+f"(d[29]), "+f"(d[30]), "+f"(d[31])
      : "r"(a[0]), "r"(a[1]), "r"(a[2]), "r"(a[3]), "r"(db), "n"(HB), "n"(1));
  }
  template <uint32_t HB>
  static __device__ __forceinline__ void set(float* d, const uint32_t* a, uint32_t db) {
    asm volatile("{\n.reg .pred p;\n.reg .b64 db;\nsetp.ne.b32 p, %38, 0;\n"
      "mov.b64 db, {%36, %37};\n"
      "wgmma.mma_async.sync.aligned.m64n64k16.f32.bf16.bf16 {"
      "%0, %1, %2, %3, %4, %5, %6, %7, %8, %9, %10, %11, %12, %13, %14, %15, "
      "%16, %17, %18, %19, %20, %21, %22, %23, %24, %25, %26, %27, %28, %29, %30, %31"
      "}, {%32, %33, %34, %35}, db, p, 1, 1, 1;\n}\n"
      : "=f"(d[0]), "=f"(d[1]), "=f"(d[2]), "=f"(d[3]), "=f"(d[4]), "=f"(d[5]), "=f"(d[6]), "=f"(d[7]),
        "=f"(d[8]), "=f"(d[9]), "=f"(d[10]), "=f"(d[11]), "=f"(d[12]), "=f"(d[13]), "=f"(d[14]), "=f"(d[15]),
        "=f"(d[16]), "=f"(d[17]), "=f"(d[18]), "=f"(d[19]), "=f"(d[20]), "=f"(d[21]), "=f"(d[22]), "=f"(d[23]),
        "=f"(d[24]), "=f"(d[25]), "=f"(d[26]), "=f"(d[27]), "=f"(d[28]), "=f"(d[29]), "=f"(d[30]), "=f"(d[31])
      : "r"(a[0]), "r"(a[1]), "r"(a[2]), "r"(a[3]), "r"(db), "n"(HB), "n"(0));
  }
};
template <> struct WgSST<48> {
  template <uint32_t HA, uint32_t HB>
  static __device__ __forceinline__ void mma(float* d, uint32_t da, uint32_t db, int sc) {
    asm volatile("{\n.reg .pred p;\n.reg .b64 da, db;\nsetp.ne.b32 p, %28, 0;\n"
      "mov.b64 da, {%24, %25};\nmov.b64 db, {%26, %27};\n"
      "wgmma.mma_async.sync.aligned.m64n48k16.f32.bf16.bf16 {"
      "%0, %1, %2, %3, %4, %5, %6, %7, %8, %9, %10, %11, %12, %13, %14, %15, "
      "%16, %17, %18, %19, %20, %21, %22, %23"
      "}, da, db, p, 1, 1, 0, 1;\n}\n"
      : "+f"(d[0]), "+f"(d[1]), "+f"(d[2]), "+f"(d[3]), "+f"(d[4]), "+f"(d[5]), "+f"(d[6]), "+f"(d[7]),
        "+f"(d[8]), "+f"(d[9]), "+f"(d[10]), "+f"(d[11]), "+f"(d[12]), "+f"(d[13]), "+f"(d[14]), "+f"(d[15]),
        "+f"(d[16]), "+f"(d[17]), "+f"(d[18]), "+f"(d[19]), "+f"(d[20]), "+f"(d[21]), "+f"(d[22]), "+f"(d[23])
      : "r"(da), "n"(HA), "r"(db), "n"(HB), "r"(sc));
  }
};
template <> struct WgSST<80> {
  template <uint32_t HA, uint32_t HB>
  static __device__ __forceinline__ void mma(float* d, uint32_t da, uint32_t db, int sc) {
    asm volatile("{\n.reg .pred p;\n.reg .b64 da, db;\nsetp.ne.b32 p, %44, 0;\n"
      "mov.b64 da, {%40, %41};\nmov.b64 db, {%42, %43};\n"
      "wgmma.mma_async.sync.aligned.m64n80k16.f32.bf16.bf16 {"
      "%0, %1, %2, %3, %4, %5, %6, %7, %8, %9, %10, %11, %12, %13, %14, %15, "
      "%16, %17, %18, %19, %20, %21, %22, %23, %24, %25, %26, %27, %28, %29, %30, %31, "
      "%32, %33, %34, %35, %36, %37, %38, %39"
      "}, da, db, p, 1, 1, 0, 1;\n}\n"
      : "+f"(d[0]), "+f"(d[1]), "+f"(d[2]), "+f"(d[3]), "+f"(d[4]), "+f"(d[5]), "+f"(d[6]), "+f"(d[7]),
        "+f"(d[8]), "+f"(d[9]), "+f"(d[10]), "+f"(d[11]), "+f"(d[12]), "+f"(d[13]), "+f"(d[14]), "+f"(d[15]),
        "+f"(d[16]), "+f"(d[17]), "+f"(d[18]), "+f"(d[19]), "+f"(d[20]), "+f"(d[21]), "+f"(d[22]), "+f"(d[23]),
        "+f"(d[24]), "+f"(d[25]), "+f"(d[26]), "+f"(d[27]), "+f"(d[28]), "+f"(d[29]), "+f"(d[30]), "+f"(d[31]),
        "+f"(d[32]), "+f"(d[33]), "+f"(d[34]), "+f"(d[35]), "+f"(d[36]), "+f"(d[37]), "+f"(d[38]), "+f"(d[39])
      : "r"(da), "n"(HA), "r"(db), "n"(HB), "r"(sc));
  }
};
template <> struct WgSST<192> {
  template <uint32_t HA, uint32_t HB>
  static __device__ __forceinline__ void mma(float* d, uint32_t da, uint32_t db, int sc) {
    asm volatile("{\n.reg .pred p;\n.reg .b64 da, db;\nsetp.ne.b32 p, %100, 0;\n"
      "mov.b64 da, {%96, %97};\nmov.b64 db, {%98, %99};\n"
      "wgmma.mma_async.sync.aligned.m64n192k16.f32.bf16.bf16 {"
      "%0, %1, %2, %3, %4, %5, %6, %7, %8, %9, %10, %11, %12, %13, %14, %15, "
      "%16, %17, %18, %19, %20, %21, %22, %23, %24, %25, %26, %27, %28, %29, %30, %31, "
      "%32, %33, %34, %35, %36, %37, %38, %39, %40, %41, %42, %43, %44, %45, %46, %47, "
      "%48, %49, %50, %51, %52, %53, %54, %55, %56, %57, %58, %59, %60, %61, %62, %63, "
      "%64, %65, %66, %67, %68, %69, %70, %71, %72, %73, %74, %75, %76, %77, %78, %79, "
      "%80, %81, %82, %83, %84, %85, %86, %87, %88, %89, %90, %91, %92, %93, %94, %95"
      "}, da, db, p, 1, 1, 0, 1;\n}\n"
      : "+f"(d[0]), "+f"(d[1]), "+f"(d[2]), "+f"(d[3]), "+f"(d[4]), "+f"(d[5]), "+f"(d[6]), "+f"(d[7]),
        "+f"(d[8]), "+f"(d[9]), "+f"(d[10]), "+f"(d[11]), "+f"(d[12]), "+f"(d[13]), "+f"(d[14]), "+f"(d[15]),
        "+f"(d[16]), "+f"(d[17]), "+f"(d[18]), "+f"(d[19]), "+f"(d[20]), "+f"(d[21]), "+f"(d[22]), "+f"(d[23]),
        "+f"(d[24]), "+f"(d[25]), "+f"(d[26]), "+f"(d[27]), "+f"(d[28]), "+f"(d[29]), "+f"(d[30]), "+f"(d[31]),
        "+f"(d[32]), "+f"(d[33]), "+f"(d[34]), "+f"(d[35]), "+f"(d[36]), "+f"(d[37]), "+f"(d[38]), "+f"(d[39]),
        "+f"(d[40]), "+f"(d[41]), "+f"(d[42]), "+f"(d[43]), "+f"(d[44]), "+f"(d[45]), "+f"(d[46]), "+f"(d[47]),
        "+f"(d[48]), "+f"(d[49]), "+f"(d[50]), "+f"(d[51]), "+f"(d[52]), "+f"(d[53]), "+f"(d[54]), "+f"(d[55]),
        "+f"(d[56]), "+f"(d[57]), "+f"(d[58]), "+f"(d[59]), "+f"(d[60]), "+f"(d[61]), "+f"(d[62]), "+f"(d[63]),
        "+f"(d[64]), "+f"(d[65]), "+f"(d[66]), "+f"(d[67]), "+f"(d[68]), "+f"(d[69]), "+f"(d[70]), "+f"(d[71]),
        "+f"(d[72]), "+f"(d[73]), "+f"(d[74]), "+f"(d[75]), "+f"(d[76]), "+f"(d[77]), "+f"(d[78]), "+f"(d[79]),
        "+f"(d[80]), "+f"(d[81]), "+f"(d[82]), "+f"(d[83]), "+f"(d[84]), "+f"(d[85]), "+f"(d[86]), "+f"(d[87]),
        "+f"(d[88]), "+f"(d[89]), "+f"(d[90]), "+f"(d[91]), "+f"(d[92]), "+f"(d[93]), "+f"(d[94]), "+f"(d[95])
      : "r"(da), "n"(HA), "r"(db), "n"(HB), "r"(sc));
  }
};

struct FftConst {
  uint32_t f[2][4], fi[4][4];
  float ta[4], tb[4];
};
__device__ __forceinline__ void cis(int m, float scale, float& c, float& s) {
  const float a = (float)m * (-6.283185307179586f * scale);
  c = __cosf(a);
  s = __sinf(a);
}
__device__ __forceinline__ void fft_tables(uint32_t (&v)[12], int tw) {
  const int row = tw >> 2, ch = tw & 3;
#pragma unroll
  for (int i = 0; i < 4; i++) {
    float c[2], s[2], x[2];
#pragma unroll
    for (int e = 0; e < 2; e++) {
      cis((((32 * (8 * ch + 2 * i + e) + 15) * (4 * row - 63) + 2048) & 4095) - 2048, 1.f / 4096, c[e], s[e]);
      float gc, gs;
      cis((((row & 15) * (8 * (ch & 1) + 2 * i + e) + 8) & 15) - 8, 1.f / 16, gc, gs);
      x[e] = (row >> 4) == (ch >> 1) ? gc : (ch >> 1) ? gs : -gs;
    }
    v[i] = pack2(c[0] * 0.125f, c[1] * 0.125f);
    v[4 + i] = pack2(s[0] * 0.125f, s[1] * 0.125f);
    v[8 + i] = pack2(x[0], x[1]);
  }
#pragma unroll
  for (int i = 0; i < 12; i++) asm volatile("" : "+r"(v[i]));
}
__device__ __forceinline__ void fft_tables_store(const uint32_t (&v)[12], uint32_t sb, int tw) {
  const int row = tw >> 2;
  const uint32_t x = ((tw ^ (row >> 1)) & 3) << 4, a = sb + OFF_FT + (16 * (row >> 3) + (row & 7)) * 64 + x;
  sts128(a, v[0], v[1], v[2], v[3]);
  sts128(a + 512, v[4], v[5], v[6], v[7]);
  sts128(sb + OFF_GT + row * 64 + x, v[8], v[9], v[10], v[11]);
}
__device__ __forceinline__ void fft_twiddles(float (&v)[4], int tw) {
#pragma unroll
  for (int i = 0; i < 2; i++) {
    float c, s;
    cis((2 * (2 * (tw & 3) + i) - 15) * (4 * (tw >> 2) - 63), 1.f / 4096, c, s);
    v[2 * i] = __fdividef(-s, 1.f + c);
    v[2 * i + 1] = s;
  }
  pin<4>(v);
}
__device__ __forceinline__ void fft_matrices(FftConst& k, uint32_t sb, int w, int lane) {
  const uint32_t x = (lane >> 1) & 3;
  const uint4 t0 = lds128(sb + OFF_TT + 512 * w + 16 * lane), t1 = lds128(sb + OFF_TT + 512 * w + 16 * (lane ^ 3));
  k.ta[0] = __uint_as_float(t0.x); k.tb[0] = __uint_as_float(t0.y); k.ta[1] = __uint_as_float(t0.z); k.tb[1] = __uint_as_float(t0.w);
  k.ta[3] = __uint_as_float(t1.x); k.tb[3] = __uint_as_float(t1.y); k.ta[2] = __uint_as_float(t1.z); k.tb[2] = __uint_as_float(t1.w);
#pragma unroll
  for (int i = 0; i < 2; i++) {
    ldsm4(k.f[i], sb + OFF_FT + (16 * w + (lane & 15)) * 64 + (((2 * i + (lane >> 4)) ^ x) << 4));
    ldsm4t(k.fi[i], sb + OFF_FT + (32 * i + lane) * 64 + ((w ^ x) << 4));
#pragma unroll
    for (int j = 0; j < 4; j++) {
      k.fi[2 + i][j] = (j & 1) ? k.fi[i][j - 1] ^ 0x80008000u : k.fi[i][j + 1];
      asm volatile("" : "+r"(k.fi[2 + i][j]));
    }
  }
}
__device__ __forceinline__ void rot(bool inv, float& x, float& y, float a, float b) {
  x = fmaf(inv ? -a : a, y, x);
  y = fmaf(inv ? -b : b, x, y);
  x = fmaf(inv ? -a : a, y, x);
}
__device__ __forceinline__ void twiddle_fwd(uint32_t (&a)[4][4], float* d, const FftConst& k) {
#pragma unroll
  for (int q = 0; q < 4; q++)
#pragma unroll
    for (int j = 0; j < 2; j++) {
      float* x = d + 8 * q + 4 * j;
      rot(j, x[0], x[2], k.ta[2 * j], k.tb[2 * j]);
      rot(j, x[1], x[3], k.ta[2 * j + 1], k.tb[2 * j + 1]);
      a[q & 2][2 * j + (q & 1)] = pack2(x[0], x[1]);
      a[(q & 2) + 1][2 * j + (q & 1)] = pack2(x[2], x[3]);
    }
}
__device__ __forceinline__ void g_step(float* d, const uint32_t (&a)[4][4], uint32_t dre, uint32_t dim) {
  WgRS<32>::set<HI_SW64>(d, a[0], dre);
  WgRS<32>::set<HI_SW64>(d + 16, a[2], dre);
  WgRS<32>::mma<HI_SW64>(d, a[1], dim);
  WgRS<32>::mma<HI_SW64>(d + 16, a[3], dim);
  wg_commit();
}

__device__ __forceinline__ void conv_channel(const FftConst& k, uint32_t sb, int c, int wg, int w, int lane) {
  const uint32_t cb = sb + off_ch(c), bars = sb + OFF_BAR;
  const uint32_t du = desc_lo(cb, 1024), dg = desc_lo(sb + OFF_GT, 16), dz = desc_lo(cb + U_BYTES, 16);
  float U[32], H[32];
  uint32_t a[4][4], e[4][4];
  const float dv = __uint_as_float(lds32(sb + OFF_D + 4 * c));
  wg_fence();
  WgRS<64>::set<HI_SW32>(H, k.f[0], du + 256);
  WgRS<64>::mma<HI_SW32>(H, k.f[1], du + 256 + 32);
  wg_commit();
  wg_wait<0>();
  pin<32>(H);
  twiddle_fwd(a, H, k);
  if (ATT_GATE && H_EARLY) mbar_wait(bars + 8 * B_ATTN, 0);
  mbar_wait(bars + 8 * (B_U + (c < 3 ? c : 3)), 0);
  TSM(w == 0 && c < 3, 7 + wg);
  wg_fence();
  WgRS<64>::set<HI_SW32>(U, k.f[0], du);
  WgRS<64>::mma<HI_SW32>(U, k.f[1], du + 32);
  wg_commit();
  g_step(H, a, dg, dg + 64);
  wg_wait<1>();
  pin<32>(U);
  twiddle_fwd(e, U, k);
  wg_fence();
  g_step(U, e, dg, dg + 64);
  wg_wait<0>();
  pin<32>(U);
  pin<32>(H);
#pragma unroll
  for (int j = 0; j < 2; j++) {
    float pr[4][2], pi[4][2];
#pragma unroll
    for (int x = 0; x < 2; x++) {
      H[4 * j + x] += dv;
#pragma unroll
      for (int m = 0; m < 4; m++) {
#pragma unroll
        for (int q = 0; q <= m; q++) {
          const int ih = 16 * (q >> 1) + 2 * (q & 1) + 4 * j + x, iu = 16 * ((m - q) >> 1) + 2 * ((m - q) & 1) + 4 * j + x;
          pr[m][x] = q ? fmaf(H[ih], U[iu], pr[m][x]) : H[ih] * U[iu];
          pi[m][x] = q ? fmaf(H[ih], U[iu + 8], pi[m][x]) : H[ih] * U[iu + 8];
          pr[m][x] = fmaf(-H[ih + 8], U[iu + 8], pr[m][x]);
          pi[m][x] = fmaf(H[ih + 8], U[iu], pi[m][x]);
        }
      }
    }
#pragma unroll
    for (int m = 0; m < 4; m++) {
      a[m & 2][2 * j + (m & 1)] = pack2(pr[m][0], pr[m][1]);
      a[(m & 2) + 1][2 * j + (m & 1)] = pack2(pi[m][0], pi[m][1]);
    }
  }
  wg_fence();
  g_step(U, a, dg + 64, dg);
  const uint32_t za = cb + U_BYTES + (8 * w + (lane & 7)) * 128 + (((lane >> 3) ^ (lane & 7)) << 4);
  const uint32_t ya = cb + (lane >> 4) * 1024 + (8 * w + (lane & 7)) * 32 + ((((lane >> 3) ^ (lane >> 2)) & 1) << 4);
  wg_sync(1 + wg);
  wg_wait<0>();
  pin<32>(U);
  TSIF(w == 0, 80 + c);
#pragma unroll
  for (int p = 0; p < 2; p++) {
#pragma unroll
    for (int i = 0; i < 4; i++) {
      const int j = i & 1;
      float* x = U + 16 * p + 4 * j + (i & 2);
      rot(!j, x[8], x[0], k.ta[2 * j], k.tb[2 * j]);
      rot(!j, x[9], x[1], k.ta[2 * j + 1], k.tb[2 * j + 1]);
      e[p][i] = pack2(x[8], x[9]);
      e[2 + p][i] = pack2(x[0], x[1]);
    }
    stsm4(za ^ (64 * p), e[p]);
    stsm4((za ^ (64 * p)) + 4096, e[2 + p]);
  }
  fence_async_smem();
  wg_sync(1 + wg);
  wg_fence();
  WgRS<64>::set<HI_SW128>(H, k.fi[0], dz);
#pragma unroll
  for (int ks = 1; ks < 4; ks++) WgRS<64>::mma<HI_SW128>(H, k.fi[ks], dz + 128 * ks);
  wg_commit();
  wg_wait<0>();
  pin<32>(H);
  TSIF(w == 0, 88 + c);
#pragma unroll
  for (int j = 0; j < 8; j++)
    a[j >> 2][j & 3] = j < 2 ? pack2(H[4 * j], H[4 * j + 1]) : pack2(H[4 * j] + H[4 * j - 6], H[4 * j + 1] + H[4 * j - 5]);
  stsm4(ya, a[0]);
  stsm4(ya + 2048, a[1]);
  fence_async_smem();
  __syncwarp();
}

__device__ __forceinline__ void prep_slab(uint4* res, const uint2* sw, uint32_t sb, int slab, int w, int lane) {
  const int t = lane & 3, tp = (lane & 7) >> 1, pos = 8 * tp + 2 * (((lane >> 3) + tp) & 3) + (lane & 1);
  const uint32_t base = sb + OFF_KVS + slab * KVS_BYTES + pos * 128;
  uint32_t kk[2][4][4], vv[2][4];
  mbar_wait(sb + OFF_BAR + 8 * (B_KV + slab), 0);
#pragma unroll
  for (int h = 0; h < 2; h++) {
#pragma unroll
    for (int j = 0; j < 4; j++) {
      const uint32_t a = base + 128 * j;
      ldsm4t(kk[h][j], a + (((w + 4 * h) ^ ((a >> 7) & 7)) << 4));
    }
    const uint32_t a = base + KVS_V;
    ldsm4t(vv[h], a + (((w + 4 * h) ^ ((a >> 7) & 7)) << 4));
  }
#pragma unroll
  for (int h = 0; h < 2; h++) {
    uint32_t (&k)[4][4] = kk[h];
    uint32_t (&v)[4] = vv[h];
    const uint32_t w0 = __byte_perm(sw[h].x, 0, 0x1010), w1 = __byte_perm(sw[h].x, 0, 0x3232);
    const uint32_t w2 = __byte_perm(sw[h].y, 0, 0x1010), w3 = __byte_perm(sw[h].y, 0, 0x3232);
#pragma unroll
    for (int m = 0; m < 4; m++)
      v[m] = bmul(badd(badd(badd(bmul(k[0][m], w3), bmul(k[1][m], w2)), bmul(k[2][m], w1)), bmul(k[3][m], w0)), v[m]);
    uint32_t a[4];
#pragma unroll
    for (int m = 0; m < 4; m++) a[m] = (t & 1) ? v[(m + 3) & 3] : v[m];
    res[h] = (t & 2) ? make_uint4(a[2], a[3], a[0], a[1]) : make_uint4(a[0], a[1], a[2], a[3]);
  }
}

__device__ __forceinline__ void prep_gate(const Params& p, int b, int w, int lane) {
  uint2 gw[5], x[4][5];
#pragma unroll
  for (int j = 0; j < 5; j++) gw[j] = ldg64(reinterpret_cast<const uint2*>(p.gate_w) + lane + 32 * j);
#pragma unroll
  for (int i = 0; i < 4; i++)
#pragma unroll
    for (int j = 0; j < 5; j++)
      x[i][j] = ldg64(reinterpret_cast<const uint2*>(p.q) + (16 * b + 4 * w + i) * (DIM / 4) + lane + 32 * j);
  float s[4];
#pragma unroll
  for (int i = 0; i < 4; i++) {
    s[i] = 0.f;
#pragma unroll
    for (int j = 0; j < 5; j++) {
      const uint32_t m0 = bmul(x[i][j].x, gw[j].x), m1 = bmul(x[i][j].y, gw[j].y);
      s[i] += (bf_lo(m0) + bf_hi(m0)) + (bf_lo(m1) + bf_hi(m1));
    }
  }
  const bool h = lane & 16, q = lane & 8;
  const float a = (h ? s[2] : s[0]) + __shfl_xor_sync(0xffffffffu, h ? s[0] : s[2], 16);
  const float c = (h ? s[3] : s[1]) + __shfl_xor_sync(0xffffffffu, h ? s[1] : s[3], 16);
  float z = (q ? c : a) + __shfl_xor_sync(0xffffffffu, q ? a : c, 8);
#pragma unroll
  for (int o = 4; o > 0; o >>= 1) z += __shfl_xor_sync(0xffffffffu, z, o);
  z = bf_lo(pack2(z, 0.f));
  if ((lane & 7) == 0) g_gate[16 * b + 4 * w + (lane >> 3)] = bf_lo(pack2(__fdividef(1.f, 1.f + __expf(-z)), 0.f));
}

__device__ __forceinline__ uint32_t bmax(uint32_t a, uint32_t b) {
  uint32_t d;
  asm("max.bf16x2 %0, %1, %2;" : "=r"(d) : "r"(a), "r"(b));
  return d;
}
__device__ __forceinline__ void softmax_two(const float (&l)[2][2], uint32_t& p0, uint32_t& p1) {
  constexpr float kScale = 0.22360679774997896f, kLog2e = 1.4426950408889634f;
  const uint32_t r0 = pack2(l[0][0], l[1][0]), r1 = pack2(l[0][1], l[1][1]);
  const uint32_t x0 = pack2(bf_lo(r0) * kScale, bf_hi(r0) * kScale), x1 = pack2(bf_lo(r1) * kScale, bf_hi(r1) * kScale);
  uint32_t m = bmax(x0, x1);
  m = bmax(m, __shfl_xor_sync(0xffffffffu, m, 1));
  m = bmax(m, __shfl_xor_sync(0xffffffffu, m, 2));
  const float m0 = bf_lo(m) * kLog2e, m1 = bf_hi(m) * kLog2e;
  p0 = pack2(ex2(bf_lo(x0) * kLog2e - m0), ex2(bf_lo(x1) * kLog2e - m0));
  p1 = pack2(ex2(bf_hi(x0) * kLog2e - m1), ex2(bf_hi(x1) * kLog2e - m1));
}

__device__ __forceinline__ void halo_read(uint32_t (&kpv)[10], uint32_t (&vpv)[10], uint32_t (&tg)[7], const uint4* hp) {
#pragma unroll
  for (int j = 0; j < 7; j++) {
    uint32_t x0, x1, x2;
    asm volatile("ld.relaxed.gpu.global.v4.u32 {%0, %1, %2, %3}, [%4];"
                 : "=r"(x0), "=r"(x1), "=r"(x2), "=r"(tg[j]) : "l"(hp + 32 * j) : "memory");
    if (j < 4) kpv[3 * j] = x0; else vpv[3 * j - 10] = x0;
    if (j < 3) kpv[3 * j + 1] = x1; else vpv[3 * j - 9] = x1;
    if (j < 3) kpv[3 * j + 2] = x2; else if (j < 6) vpv[3 * j - 8] = x2;
  }
}

template <int ROT>
__device__ __forceinline__ void pack_qkv(const float* acc, uint32_t (&qlo)[10], uint32_t (&qhi)[10], uint32_t (&klo)[10],
                                         uint32_t (&khi)[10], uint32_t (&vlo)[10], uint32_t (&vhi)[10]) {
#pragma unroll
  for (int j = 0; j < 10; j++) {
    const int x = (j + ROT) % 10, tq = x < 8 ? x : 16 + x, tk = x < 8 ? 8 + x : 18 + x, tv = x < 8 ? 16 + x : 20 + x;
    khi[j] = pack2(acc[4 * tk + 2], acc[4 * tk + 3]);
    vhi[j] = movm(pack2(acc[4 * tv + 2], acc[4 * tv + 3]));
    qlo[j] = pack2(acc[4 * tq], acc[4 * tq + 1]);
    qhi[j] = pack2(acc[4 * tq + 2], acc[4 * tq + 3]);
    klo[j] = pack2(acc[4 * tk], acc[4 * tk + 1]);
    vlo[j] = pack2(acc[4 * tv], acc[4 * tv + 1]);
    asm volatile("" : "+r"(khi[j]), "+r"(qlo[j]), "+r"(qhi[j]), "+r"(klo[j]), "+r"(vlo[j]));
  }
}

template <int ROT> __device__ __forceinline__ void halo_send(const float* acc, uint4* ho, uint32_t tag) {
#pragma unroll
  for (int j = 0; j < 7; j++) {
    uint32_t x[3];
#pragma unroll
    for (int e = 0; e < 3; e++) {
      const int i = 3 * j + e, y = (i % 10 + ROT) % 10, tk = y < 8 ? 8 + y : 18 + y, tv = y < 8 ? 16 + y : 20 + y;
      x[e] = i < 10 ? pack2(acc[4 * tk + 2], acc[4 * tk + 3]) : i < 20 ? movm(pack2(acc[4 * tv + 2], acc[4 * tv + 3])) : 0u;
    }
    asm volatile("st.relaxed.gpu.global.v4.u32 [%0], {%1, %2, %3, %4};" ::"l"(ho + 32 * j), "r"(x[0]), "r"(x[1]), "r"(x[2]), "r"(tag) : "memory");
  }
}

__device__ __forceinline__ void attention(float* acc, uint32_t sb, int b, int par, int w, int lane, uint32_t tag) {
  const int g = lane >> 2, t = lane & 3;
  uint32_t klo[10], khi[10], vlo[10], vhi[10], qlo[10], qhi[10], kpv[10], vpv[10];
  if (HALO_FIRST && w == 3 && b < NCTA - 8) {
    uint4* ho = g_halo + (b * 2 + par) * 224 + lane;
    if (tail_first(b & 7)) halo_send<8>(acc, ho, tag);
    else halo_send<0>(acc, ho, tag);
    TSIF(par == 0, 76);
    pin<120>(acc);
  }
  if (tail_first(b & 7)) pack_qkv<8>(acc, qlo, qhi, klo, khi, vlo, vhi);
  else pack_qkv<0>(acc, qlo, qhi, klo, khi, vlo, vhi);
  const uint32_t xa = sb + OFF_KVX + (par * 3) * 2560 + lane * 16;
  if (w < 3) {
    sts128(xa + w * 2560, khi[0], khi[1], khi[2], khi[3]);
    sts128(xa + w * 2560 + 512, khi[4], khi[5], khi[6], khi[7]);
    sts128(xa + w * 2560 + 1024, khi[8], khi[9], vhi[0], vhi[1]);
    sts128(xa + w * 2560 + 1536, vhi[2], vhi[3], vhi[4], vhi[5]);
    sts128(xa + w * 2560 + 2048, vhi[6], vhi[7], vhi[8], vhi[9]);
  } else if (!HALO_FIRST && b < NCTA - 8) {
    uint4* ho = g_halo + (b * 2 + par) * 224 + lane;
#pragma unroll
    for (int j = 0; j < 7; j++) {
      const uint32_t x0 = j < 4 ? khi[3 * j] : vhi[3 * j - 10], x1 = j < 3 ? khi[3 * j + 1] : vhi[3 * j - 9];
      const uint32_t x2 = j < 3 ? khi[3 * j + 2] : j < 6 ? vhi[3 * j - 8] : 0u;
      asm volatile("st.relaxed.gpu.global.v4.u32 [%0], {%1, %2, %3, %4};" ::"l"(ho + 32 * j), "r"(x0), "r"(x1), "r"(x2), "r"(tag) : "memory");
    }
  }
  TSIF(par == 0 && w == 1, 64);
  TSIF(par == 0 && w == 3 && !HALO_FIRST, 76);
#pragma unroll
  for (int j = 0; j < 10; j++) vlo[j] = movm(vlo[j]);
  const bool far0 = 2 * t > g, far1 = 2 * t + 1 > g;
  const uint32_t mfar = (far0 ? 0x0000FFFFu : 0u) | (far1 ? 0xFFFF0000u : 0u);
  float slo[4][2], shi[4][2], lg[2][2];
  uint32_t phi[4], plo[4], qml[4], qmh[4];
#pragma unroll
  for (int h = 0; h < 4; h++) {
    const int f = h == 0 ? 0 : h == 1 ? 3 : h == 2 ? 5 : 8, hf = h < 2 ? 2 : 7;
    const bool mine = (h & 1) ? t >= 2 : t < 2;
    qml[h] = mine ? qlo[hf] : 0u;
    qmh[h] = mine ? qhi[hf] : 0u;
    float a[4] = {0.f, 0.f, 0.f, 0.f}, c[4] = {0.f, 0.f, 0.f, 0.f};
    mma16816(a, qlo[f], qhi[f], qlo[f + 1], qhi[f + 1], klo[f], klo[f + 1]);
    mma16816(c, qlo[f], qhi[f], qlo[f + 1], qhi[f + 1], khi[f], khi[f + 1]);
    mma1688(a, qml[h], qmh[h], klo[hf]);
    mma1688(c, qml[h], qmh[h], khi[hf]);
    slo[h][0] = a[0];
    slo[h][1] = a[1];
    shi[h][0] = lg[h & 1][0] = far0 ? a[2] : c[2];
    shi[h][1] = lg[h & 1][1] = far1 ? a[3] : c[3];
    if (!ATT_MERGE && (h & 1)) softmax_two(lg, phi[h - 1], phi[h]);
  }
  TSIF(par == 0 && w == 1, 65);
  wg_sync(1 + par);
  TSIF(par == 0 && w == 1, 66);
  const bool nohist = (w == 0) && (b < 8);
  const uint4* hp = g_halo + ((b - 8) * 2 + par) * 224 + lane;
  uint32_t tg[7];
  if (w > 0) {
    const uint4 v0 = lds128(xa + (w - 1) * 2560), v1 = lds128(xa + (w - 1) * 2560 + 512), v2 = lds128(xa + (w - 1) * 2560 + 1024);
    const uint4 v3 = lds128(xa + (w - 1) * 2560 + 1536), v4 = lds128(xa + (w - 1) * 2560 + 2048);
    kpv[0] = v0.x; kpv[1] = v0.y; kpv[2] = v0.z; kpv[3] = v0.w; kpv[4] = v1.x; kpv[5] = v1.y; kpv[6] = v1.z; kpv[7] = v1.w;
    kpv[8] = v2.x; kpv[9] = v2.y; vpv[0] = v2.z; vpv[1] = v2.w; vpv[2] = v3.x; vpv[3] = v3.y; vpv[4] = v3.z; vpv[5] = v3.w;
    vpv[6] = v4.x; vpv[7] = v4.y; vpv[8] = v4.z; vpv[9] = v4.w;
  } else if (nohist) {
#pragma unroll
    for (int j = 0; j < 10; j++) kpv[j] = vpv[j] = 0u;
  } else {
    TSIF(par == 0, 77);
    halo_read(kpv, vpv, tg, hp);
  }
  if (w == 0 && !nohist) {
    int spins = 0;
    while (true) {
      bool ok = true;
#pragma unroll
      for (int j = 0; j < 7; j++) ok = ok && tg[j] == tag;
      if (__all_sync(0xffffffffu, ok) || ++spins > SPIN_LIMIT) break;
      halo_read(kpv, vpv, tg, hp);
    }
    TSIF(par == 0, 79);
  }
#pragma unroll
  for (int h = 0; h < 4; h++) {
    const int f = h == 0 ? 0 : h == 1 ? 3 : h == 2 ? 5 : 8, hf = h < 2 ? 2 : 7;
    float a[4] = {0.f, 0.f, 0.f, 0.f};
    mma16816(a, qlo[f], qhi[f], qlo[f + 1], qhi[f + 1], kpv[f], kpv[f + 1]);
    mma1688(a, qml[h], qmh[h], kpv[hf]);
    const float ninf = __int_as_float(0xff800000);
    lg[h & 1][0] = far0 ? (nohist ? ninf : a[0]) : slo[h][0];
    lg[h & 1][1] = far1 ? (nohist ? ninf : a[1]) : slo[h][1];
    if (h & 1) {
      softmax_two(lg, plo[h - 1], plo[h]);
      if (ATT_MERGE) {
        const float lh[2][2] = {{shi[h - 1][0], shi[h - 1][1]}, {shi[h][0], shi[h][1]}};
        softmax_two(lh, phi[h - 1], phi[h]);
      }
    }
  }
  TSIF(par == 0 && w <= 1, 67 + w);
  uint32_t ov[20];
#pragma unroll
  for (int hp = 0; hp < 2; hp++) {
    const int hf = hp ? 7 : 2;
    float sh[4] = {0.f, 0.f, 0.f, 0.f}, i0 = 0.f, i1 = 0.f;
#pragma unroll
    for (int e = 0; e < 2; e++) {
      const int h = 2 * hp + e, f = h == 0 ? 0 : h == 1 ? 3 : h == 2 ? 5 : 8;
      const uint32_t a0 = plo[h] & mfar, a2 = plo[h] & ~mfar, a3 = phi[h] & mfar, c1 = phi[h] & ~mfar;
      float sum[4] = {0.f, 0.f, 0.f, 0.f};
      mma1688(sum, plo[h], phi[h], 0x3F803F80u);
      const float r0 = rcp(sum[0]), r1 = rcp(sum[2]);
#pragma unroll
      for (int j = f; j < f + 2; j++) {
        float o[4] = {0.f, 0.f, 0.f, 0.f};
        mma16816(o, a0, 0u, a2, a3, vpv[j], vlo[j]);
        mma1688(o, 0u, c1, vhi[j]);
        ov[2 * j] = pack2(o[0] * r0, o[1] * r0);
        ov[2 * j + 1] = pack2(o[2] * r1, o[3] * r1);
      }
      const bool mine = e ? g >= 4 : g < 4;
      mma16816(sh, a0, 0u, a2, a3, mine ? vpv[hf] : 0u, mine ? vlo[hf] : 0u);
      mma1688(sh, 0u, c1, mine ? vhi[hf] : 0u);
      if (e == 0 || t >= 2) {
        i0 = r0;
        i1 = r1;
      }
    }
    ov[2 * hf] = pack2(sh[0] * i0, sh[1] * i0);
    ov[2 * hf + 1] = pack2(sh[2] * i1, sh[3] * i1);
  }
  TS(32 + 4 * par + w);
  mbar_wait(sb + OFF_BAR + 8 * B_P1, 0);
  const uint32_t oa = sb + OFF_OA + (lane >> 4) * 2048 + (32 * w + 2 * (lane & 15) + par) * 16;
#pragma unroll
  for (int j = 0; j < 5; j++) stsm4(oa + 4096 * j, ov + 4 * j);
  TSIF(par == 0 && w == 0, 120);
  fence_async_smem();
  TSIF(par == 0 && w == 0, 121);
  __syncwarp();
  if (lane == 0) mbar_arrive(sb + OFF_BAR + 8 * B_ATTN);
  TSM(w == 0 || w == 2, 122 + par + (w == 2 ? 3 : 0));
}

struct Maps {
  CUtensorMap x, wm, wt, k, v, y, wo, qm, qt, om, ot, u;
};

__device__ __forceinline__ void load_stage(uint32_t sb, int kb, int b, const Maps& m) {
  const uint32_t st = sb + (kb & 3) * STAGE_BYTES, bar = sb + OFF_BAR + 8 * (B_FULL1 + (kb & 3));
  const int r = b >> 3, hg = b & 7, slab = kb - KV_KB;
  const bool kv = slab >= 0 && slab < 5;
  const uint32_t kbar = sb + OFF_BAR + 8 * (B_KV + slab), dst = sb + OFF_KVS + slab * KVS_BYTES;
  mbar_expect_tx(bar, STAGE_BYTES);
  if (kv) mbar_expect_tx(kbar, KVS_BYTES);
  tma_3d(st, &m.x, 64 * kb, 64 * r, 0, bar);
  if (kv && KV_MIX) tma_3d(dst, &m.k, 0, 32 * (b >> 1) - 3, 2 * slab + (b & 1), kbar);
  tma_3d(st + ST_W, &m.wm, 80 * hg + (tail_first(hg) ? 16 : 0), 64 * kb, 0, bar);
  if (kv && KV_MIX) tma_3d(dst + KVS_V, &m.v, 0, 32 * (b >> 1), 2 * slab + (b & 1), kbar);
  tma_3d(st + ST_WT, &m.wt, 80 * hg + (tail_first(hg) ? 0 : 64), 64 * kb, 0, bar);
  if (kv && !KV_MIX) tma_3d(dst, &m.k, 0, 32 * (b >> 1) - 3, 2 * slab + (b & 1), kbar);
  if (kv && !KV_MIX) tma_3d(dst + KVS_V, &m.v, 0, 32 * (b >> 1), 2 * slab + (b & 1), kbar);
}

__global__ void __launch_bounds__(NTHR, 1) fused_kernel(const __grid_constant__ Maps m, const Params p) {
  extern __shared__ __align__(1024) uint8_t smem[];
  const uint32_t sb = (uint32_t)__cvta_generic_to_shared(smem);
  const uint32_t bars = sb + OFF_BAR;
  const int tid = threadIdx.x, lane = tid & 31;
  int b = blockIdx.x;
  if (BMAP == 1) b = (((b & 63) >> 3) * 2 + (b & 1)) * 8 + (((b < 64 ? 0x6521 : 0x7430) >> (4 * ((b >> 1) & 3))) & 7);
  if (BMAP == 2) b = ((b & 63) >> 2) * 8 + (((b < 64 ? 0x6521 : 0x7430) >> (4 * (b & 3))) & 7);
  if (BMAP == 3) b = (((b & 63) >> 3) * 2 + (b & 1)) * 8 + (((b < 64 ? 0x7430 : 0x6521) >> (4 * ((b >> 1) & 3))) & 7);
  if (BMAP == 4) b = (((b >> 4) * 2 + (b & 1)) * 8) + ((b >> 1) & 7);
  if (BMAP == 5) b = 127 - b;
  const int r = b >> 3, hg = b & 7;

  if (tid == T_ISSUE) {
    TSM(true, 0);
#pragma unroll
    for (int i = 0; i < 4; i++) mbar_init(bars + 8 * (B_FULL1 + i), 1);
#pragma unroll
    for (int i = 0; i < 3; i++) mbar_init(bars + 8 * (B_KV + i), 1);
    fence_async_smem();
#pragma unroll 1
    for (int kb = 0; kb <= PRE2; kb++) load_stage(sb, kb, b, m);
  } else if (tid >= T_PF && tid < T_PF + 12) {
    tm_prefetch(&m.x + (tid - T_PF));
  } else if (tid == T_INIT) {
#pragma unroll
    for (int i = 0; i < 4; i++) mbar_init(bars + 8 * (B_EMPTY1 + i), 8);
#pragma unroll
    for (int i = 0; i < 8; i++) mbar_init(bars + 8 * (B_FULL2 + i), 1);
#pragma unroll
    for (int i = 0; i < 4; i++) mbar_init(bars + 8 * (B_EMPTY2 + i), 8);
#pragma unroll
    for (int i = 0; i < 4; i++) mbar_init(bars + 8 * (B_U + i), 1);
    mbar_init(bars + 8 * B_HA, 4);
    mbar_init(bars + 8 * B_GATE, 4);
    mbar_init(bars + 8 * B_HB, 1);
    mbar_init(bars + 8 * B_KVD, 4);
    mbar_init(bars + 8 * B_QF, 1);
    mbar_init(bars + 8 * B_ATTN, 8);
    mbar_init(bars + 8 * B_P1, 8);
    mbar_init(bars + 8 * B_C34, 1);
#pragma unroll
    for (int i = 0; i < 5; i++) mbar_init(bars + 8 * (B_YST + i), 4);
#pragma unroll
    for (int i = 0; i < 5; i++) mbar_init(bars + 8 * (B_US + i), 4);
    mbar_init(bars + 8 * B_YSIG, 1);
    mbar_init(bars + 8 * B_YFULL, 1);
    mbar_init(bars + 8 * B_EPOCH, 1);
    mbar_init(bars + 8 * B_PREP, 4);
    mbar_init(bars + 8 * B_USIG, 1);
    mbar_init(bars + 8 * B_WST, 1);
#pragma unroll
    for (int i = 3; i < 5; i++) mbar_init(bars + 8 * (B_KV + i), 1);
    mbar_init(bars + 8 * B_E3, 8);
    mbar_init(bars + 8 * B_LAST, 1);
    mbar_init(bars + 8 * B_OSIG, 1);
    mbar_init(bars + 8 * B_WOP, 1);
    fence_async_smem();
  }
  const int warp = __shfl_sync(0xffffffffu, tid >> 5, 0), wg = warp >> 2, w = warp & 3;
  __syncthreads();

  if (wg == 3) {
    asm volatile("setmaxnreg.dec.sync.aligned.u32 56;");
    if (w == 0) {
      if (lane == 0) {
#pragma unroll 1
        for (int kb = 1 + PRE2; kb < 10; kb++) {
          if (kb >= 4) mbar_wait(bars + 8 * (kb == 7 ? B_E3 : B_EMPTY1 + (kb & 3)), (kb >> 3) & 1);
          TSIF(kb >= 4, 44 + kb);
          load_stage(sb, kb, b, m);
          TSIF(kb == 3, 60);
          if (kb == TRIG_KB) mbar_arrive(bars + 8 * B_LAST);
        }
        mbar_wait(bars + 8 * B_WOP, 0);
        mbar_wait(bars + 8 * WL_TRIG, 0);
        mbar_wait(bars + 8 * B_EPOCH, 0);
        flag_wait(g_cnt + C_W + 32 * hg, (lds32(sb + OFF_EPOCH) + 1) * 16);
        TS(30);
#pragma unroll 1
        for (int j = 0; j < 8; j++) {
          if (j >= 6) mbar_wait(bars + 8 * (B_EMPTY2 + j - 6), 0);
          if (j == 4) mbar_wait(bars + 8 * B_ATTN, 0);
          TSIF(j >= 6, 100 + j);
          if (RF_GATE && j == 6) mbar_wait(bars + 8 * B_YSIG, 0);
          mbar_expect_tx(bars + 8 * (B_FULL2 + j), j == 0 ? WO_BYTES : j == 5 ? O_BYTES + WO_BYTES + 512 : O_BYTES + WO_BYTES);
          bulk_load(sb + off_w(j), g_WO + (hg * 8 + step_src(hg, j)) * 800, WO_BYTES, bars + 8 * (B_FULL2 + j));
        }
        mbar_wait(bars + 8 * (B_EMPTY2 + 3), 0);
        mbar_expect_tx(bars + 8 * B_QF, O_BYTES);
        tma_2d(sb + OFF_QS, &m.qm, 80 * hg, 128 * r, bars + 8 * B_QF);
        tma_2d(sb + OFF_QT, &m.qt, 80 * hg + 64, 128 * r, bars + 8 * B_QF);
      }
    } else if (w == 1) {
      unsigned epoch = 0;
      if (lane == 0) {
        epoch = atomicAdd(g_cnt + C_LAUNCH, 1u) / NCTA;
        asm volatile("st.shared.u32 [%0], %1;" ::"r"(sb + OFF_EPOCH), "r"(epoch) : "memory");
        mbar_arrive(bars + 8 * B_EPOCH);
        mbar_wait(bars + 8 * B_KVD, 0);
        mbar_expect_tx(bars + 8 * B_HB, 5 * 4096);
#pragma unroll 1
        for (int c = 0; c < 5; c++) {
          if (c == 3) mbar_wait(bars + 8 * B_S3, 0);
          bulk_load(sb + off_ch(c) + U_BYTES, p.ssm_k + (5 * b + c) * SEQ, 4096, bars + 8 * B_HB);
        }
#pragma unroll
        for (int c = 0; c < 4; c++) mbar_expect_tx(bars + 8 * (B_U + c), c < 3 ? U_BYTES : 2 * U_BYTES);
        const uint4* usrc = g_U + 5 * b * U_PITCH;
        mbar_wait(bars + 8 * B_USIG, 0);
        flag_wait(g_cnt + C_PREP + 32 * (b & 15), (epoch + 1) * NCTA);
        TS(23);
#pragma unroll
        for (int c = 0; c < 5; c++) {
          if (c == 3) mbar_wait(bars + 8 * (B_U + 2), 0);
          bulk_load(sb + off_ch(c), usrc + c * U_PITCH, U_BYTES, bars + 8 * (B_U + (c < 3 ? c : 3)));
          TSIF(c == 0 || c == 4, 116 + (c >> 2));
        }
      }
      epoch = __shfl_sync(0xffffffffu, epoch, 0);
      if (lane < 8) {
        const int src = (b & ~7) | step_src(hg, lane);
        mbar_wait(bars + 8 * B_OSIG, 0);
        TS(20);
        flag_wait(g_cnt + C_O + 32 * src, epoch + 1);
        if (lane >= 1 && lane < 4) bulk_load(sb + off_o(lane), g_O + src * 1280, O_BYTES, bars + 8 * (B_FULL2 + lane));
        __syncwarp(0xff);
        TS(21);
        if (lane == 5) bulk_load(sb + OFF_GATE, g_gate + 128 * r, 512, bars + 8 * (B_FULL2 + 5));
#pragma unroll 1
        for (int j = 4; j < 8; j++) {
          if (lane == j) {
            mbar_wait(bars + 8 * (j < 6 ? B_C34 : B_EMPTY2 + j - 6), 0);
            if (RF_GATE && j == 6) mbar_wait(bars + 8 * B_YSIG, 0);
            bulk_load(sb + off_o(j), g_O + src * 1280, O_BYTES, bars + 8 * (B_FULL2 + j));
          }
          __syncwarp(0xff);
        }
        TS(22);
      }
    } else if (w == 2) {
      mbar_wait(bars + 8 * B_PREP, 0);
      flag_signal(g_cnt + C_PREP, 16, lane);
      TS(25);
      if (lane == 0) mbar_arrive(bars + 8 * B_USIG);
      mbar_wait(bars + 8 * B_GATE, 0);
      if ((NOMB & 1) && lane == 0) asm volatile("fence.release.gpu;" ::: "memory");
      mbar_wait(bars + 8 * B_ATTN, 0);
      if (lane == 0) {
        if (O_DEFER) mbar_wait(bars + 8 * (B_U + 3), 0);
        asm volatile("cp.async.bulk.global.shared::cta.bulk_group [%0], [%1], 20480;\ncp.async.bulk.commit_group;\n"
                     "cp.async.bulk.wait_group 0;\nfence.proxy.async.global;" ::"l"(g_O + b * 1280), "r"(sb + OFF_OA) : "memory");
      }
      TS(74);
      if (!(NOMB & 1)) flag_signal(g_cnt + C_O + 32 * b, 1, lane);
      else if (lane == 0) flag_bump(g_cnt + C_O + 32 * b);
      TS(26);
      if (lane == 0) mbar_arrive(bars + 8 * B_OSIG);

    } else {
      if (lane == 0) {
        uint4* dst = g_WO + (hg * 8 + (r >> 1)) * 800 + (r & 1) * 80;
        mbar_wait(bars + 8 * B_P1, 0);
        mbar_wait(bars + 8 * WB_TRIG, 0);
        mbar_expect_tx(bars + 8 * B_WST, WO_BYTES / 2);
        tma_3d(sb + OFF_WS, &m.wo, 0, 40 * r, 5 * hg, bars + 8 * B_WST);
        mbar_wait(bars + 8 * B_WST, 0);
        mbar_wait(bars + 8 * WO_TRIG, 0);
#pragma unroll 1
        for (int n = 0; n < 5; n++)
          asm volatile("cp.async.bulk.global.shared::cta.bulk_group [%0], [%1], 1280;" ::"l"(dst + 160 * n), "r"(sb + OFF_WS + 1280 * n) : "memory");
        asm volatile("cp.async.bulk.commit_group;\ncp.async.bulk.wait_group 0;\nfence.proxy.async.global;" ::: "memory");
        if (!(NOMB & 4)) asm volatile("fence.release.gpu;" ::: "memory");
        flag_bump(g_cnt + C_W + 32 * hg);
        mbar_arrive(bars + 8 * B_WOP);
        TS(71);
#pragma unroll 1
        for (int c = 0; c < 5; c++) {
          mbar_wait(bars + 8 * (B_YST + c), 0);
          asm volatile("cp.async.bulk.global.shared::cta.bulk_group [%0], [%1], 4096;\ncp.async.bulk.commit_group;"
                       ::"l"(g_Y + (5 * b + c) * Y_PITCH), "r"(sb + off_ch(c)) : "memory");
          if (c == 2) {
            asm volatile("cp.async.bulk.wait_group.read 0;" ::: "memory");
            mbar_arrive(bars + 8 * B_C34);
          }
        }
        asm volatile("cp.async.bulk.wait_group 0;\nfence.proxy.async.global;" ::: "memory");
        TS(75);
        if (!(NOMB & 2)) asm volatile("fence.release.gpu;" ::: "memory");
        flag_bump(g_cnt + C_Y + 32 * (b >> 4));
        TS(27);
        mbar_arrive(bars + 8 * B_YSIG);
        mbar_expect_tx(bars + 8 * B_YFULL, 20480);
        flag_wait(g_cnt + C_Y + 32 * hg, (lds32(sb + OFF_EPOCH) + 1) * 16);
        TS(24);
        tma_2d(sb + OFF_YT, &m.y, 128 * r, 80 * hg, bars + 8 * B_YFULL);
        tma_2d(sb + OFF_YT + 10240, &m.y, 128 * r + 64, 80 * hg, bars + 8 * B_YFULL);
      }
    }
  } else {
    asm volatile("setmaxnreg.inc.sync.aligned.u32 152;");
    if (wg < 2) {
      float acc[120];
#pragma unroll
      for (int i = 0; i < 120; i++) acc[i] = 0.f;
      const uint32_t da = desc_lo(sb + wg * 8192, 16), db = desc_lo(sb + ST_W, 8192), dc = desc_lo(sb + ST_WT, 2048);
      if (PW1) pin<120>(acc);
      if (PW1 == 2) mbar_wait(bars + 8 * B_FULL1, 0);
#pragma unroll 1
      for (int kb = 0; kb < 10; kb++) {
        mbar_wait(bars + 8 * (B_FULL1 + (kb & 3)), (kb >> 2) & 1);
        const uint32_t so = (kb & 3) * (STAGE_BYTES >> 4);
        wg_fence();
#pragma unroll
        for (int k = 0; k < 4; k++) {
          WgSST<192>::mma<HI_SW128, HI_SW128>(acc, da + so + 2 * k, db + so + 128 * k, 1);
          WgSST<48>::mma<HI_SW128, HI_SW32>(acc + 96, da + so + 2 * k, dc + so + 32 * k, 1);
        }
        wg_commit();
        wg_wait<1>();
        if (kb > 0 && lane == 0) mbar_arrive(bars + 8 * (kb == 4 ? B_E3 : B_EMPTY1 + ((kb - 1) & 3)));
      }
      mbar_wait(bars + 8 * B_EPOCH, 0);
      const uint32_t tag = lds32(sb + OFF_EPOCH) + 1;
      mbar_wait(bars + 8 * B_S3, 0);
      wg_wait<0>();
      pin<120>(acc);
      if (lane == 0) mbar_arrive(bars + 8 * B_P1);
      TSM(w == 0, 3 + wg);
      attention(acc, sb, b, wg, w, lane, tag);
    } else {
      const int tw = tid & 127, chl = 64 * (b & 1) + 8 * w + (lane >> 2);
      uint4* up = g_U + chl * U_PITCH + ((4 * (b >> 1) + (lane & 3)) ^ ((b >> 2) & 1));
      uint2 sw[10];
      uint32_t dv = 0;
      if (lane < 5) dv = __ldg(reinterpret_cast<const unsigned short*>(p.ssm_D) + 5 * b + lane);
#pragma unroll
      for (int i = 0; i < 10; i++) sw[i] = ldg64(reinterpret_cast<const uint2*>(p.shift_k) + chl + 128 * (i >> 1) + 32 * (i & 1));
      uint32_t tab[12];
      float tt[4];
      fft_tables(tab, tw);
      fft_twiddles(tt, tw);
      uint4 res[10];
#pragma unroll
      for (int i = 0; i < 10; i++) res[i] = make_uint4(0, 0, 0, 0);
#pragma unroll 1
      for (int slab = 0; slab < 5; slab++) {
#pragma unroll
        for (int i = 0; i < 8; i++) res[i] = res[i + 2];
        prep_slab(res + 8, sw, sb, slab, w, lane);
        TSIF(w == 0, 99 + 4 * slab);
#pragma unroll
        for (int i = 0; i < 8; i++) sw[i] = sw[i + 2];
      }
      TSIF(w == 0, 28);
      __syncwarp();
      if (lane == 0) mbar_arrive(bars + 8 * B_KVD + ((res[8].x ^ res[9].x) & p.zero));
      mbar_wait(bars + 8 * B_KVD, 0);
      fft_tables_store(tab, sb, tw);
      mbar_wait(bars + 8 * B_LAST, 0);
#pragma unroll
      for (int i = 0; i < 10; i++) up[(128 * (i >> 1) + 32 * (i & 1)) * U_PITCH] = res[i];
      __syncwarp();
      if (lane == 0) mbar_arrive(bars + 8 * B_PREP);
      TSIF(w == 0 && !U_TMA, 5);
      mbar_wait(bars + 8 * (G_AFTER ? B_USIG : B_LAST), 0);
      prep_gate(p, b, w, lane);
      __syncwarp();
      if (lane == 0) mbar_arrive(bars + 8 * B_GATE);
      TSIF(w == 0, 72);
      mbar_wait(bars + 8 * B_HB, 0);
      TSIF(w == 0, 2);
      const uint32_t ha = sb + U_BYTES + ((tw >> 3) * 16 + 8 + (tw & 7)) * 16;
      uint4 hv[5];
#pragma unroll
      for (int c = 0; c < 5; c++) hv[c] = lds128(ha + off_ch(c));
      __syncwarp();
#pragma unroll
      for (int c = 0; c < 5; c++) sts128((ha ^ 16) + off_ch(c), hv[c].x, hv[c].y, hv[c].z, hv[c].w);
      sts128(sb + OFF_TT + 16 * tw, __float_as_uint(tt[0]), __float_as_uint(tt[1]), __float_as_uint(tt[2]), __float_as_uint(tt[3]));
      if (tw < 5) asm volatile("st.shared.f32 [%0], %1;" ::"r"(sb + OFF_D + 4 * tw), "f"(bf_lo(dv) * 0.125f) : "memory");
      fence_async_smem();
      __syncwarp();
      if (lane == 0) mbar_arrive(bars + 8 * B_HA);
      TSIF(w == 0, 6);
    }

    FftConst fc;
    TSM(w == 0 && wg == 0, 104);
    mbar_wait(bars + 8 * B_HA, 0);
    fft_matrices(fc, sb, w, lane);
    TSM(w == 0 && wg == 0, 105);
    if (ATT_GATE && !H_EARLY) mbar_wait(bars + 8 * B_ATTN, 0);
    TSM(w == 0 && wg == 2, 124);
#pragma unroll 1
    for (uint32_t tasks = wg == 0 ? TASK0 : wg == 1 ? TASK1 : TASK2; tasks; tasks >>= 4) {
      const int c = (tasks & 7) - 1;
      conv_channel(fc, sb, c, wg, w, lane);
      if (lane == 0) mbar_arrive(bars + 8 * (B_YST + c));
      TSM(w == 0, 10 + c);
    }

    if (wg < 2) {
      const int g = lane >> 2;
      float acc[40];
#pragma unroll
      for (int i = 0; i < 40; i++) acc[i] = 0.f;
      const uint32_t da = desc_lo(sb + wg * 1024, 2048), db = desc_lo(sb, 2560);
      mbar_wait(bars + 8 * B_ATTN, 0);
      mbar_wait(bars + 8 * (B_YST + 3), 0);
      mbar_wait(bars + 8 * (B_YST + 4), 0);
      if (PW2) mbar_wait(bars + 8 * B_FULL2, 0);
      TSM(w == 0, 15 + wg);
#pragma unroll 1
      for (int j = 0; j < 8; j++) {
        mbar_wait(bars + 8 * (B_FULL2 + j), 0);
        const uint32_t oa = da + (off_o(j) >> 4), ob = db + (off_w(j) >> 4);
        wg_fence();
#pragma unroll
        for (int k = 0; k < 5; k++) WgSST<80>::mma<HI_NONE, HI_SW32>(acc, oa + 256 * k, ob + 32 * k, 1);
        wg_commit();
        wg_wait<1>();
        if (j >= 1 && j <= 4 && lane == 0) mbar_arrive(bars + 8 * (B_EMPTY2 + j - 1));
      }
      TSIF(w == 0 && wg == 0, 113);
      const int tr = 64 * wg + 16 * w + (lane & 15);
      const uint32_t fm = sb + OFF_QS + tr * 128, fx = (lane >> 4) ^ (tr & 7);
      const uint32_t ft = sb + OFF_QT + tr * 32 + (((lane >> 4) ^ (tr >> 2)) & 1) * 16;
      const float g0 = __uint_as_float(lds32(sb + OFF_GATE + (64 * wg + 16 * w + g) * 4));
      const float g1 = __uint_as_float(lds32(sb + OFF_GATE + (64 * wg + 16 * w + 8 + g) * 4));
      const uint32_t ga = pack2(g0, g0), gb = pack2(g1, g1);
      const uint32_t na = pack2(1.f - g0, 1.f - g0), nb = pack2(1.f - g1, 1.f - g1);

      wg_wait<0>();
      pin<40>(acc);
      TSM(w == 0, 17 + wg);
      uint32_t pb[20];
#pragma unroll
      for (int j = 0; j < 10; j++) {
        pb[2 * j] = bmul(na, pack2(acc[4 * j], acc[4 * j + 1]));
        pb[2 * j + 1] = bmul(nb, pack2(acc[4 * j + 2], acc[4 * j + 3]));
        asm volatile("" : "+r"(pb[2 * j]), "+r"(pb[2 * j + 1]));
      }
      const uint32_t ya = sb + OFF_YT + wg * 10240 + ((lane >> 4) * 8 + (lane & 7)) * 128 +
                          (((2 * w + (((lane >> 3) & 1) ^ wg)) ^ (lane & 7)) << 4);
      uint32_t qf[20];
      mbar_wait(bars + 8 * B_QF, 0);
#pragma unroll
      for (int j = 0; j < 5; j++) ldsm4(qf + 4 * j, j < 4 ? fm + ((fx ^ (2 * j)) << 4) : ft);
      mbar_wait(bars + 8 * B_YFULL, 0);
      TSM(w == 0 && wg == 0, 19);
#pragma unroll
      for (int j = 0; j < 5; j++) {
        uint32_t y[4];
        ldsm4t(y, ya + 2048 * j);
#pragma unroll
        for (int i = 0; i < 4; i++) qf[4 * j + i] = badd(bmul((i & 1) ? gb : ga, bmul(qf[4 * j + i], y[i])), pb[4 * j + i]);
      }
#pragma unroll
      for (int j = 0; j < 5; j++) stsm4(j < 4 ? fm + ((fx ^ (2 * j)) << 4) : ft, qf + 4 * j);
      fence_async_smem();
      __syncwarp();
      if (lane == 0) {
        const int row = 64 * wg + 16 * w;
        asm volatile("cp.async.bulk.tensor.2d.global.shared::cta.bulk_group [%0, {%2, %3}], [%1];"
                     ::"l"(&m.om), "r"(sb + OFF_QS + row * 128), "r"(80 * hg), "r"(128 * r + row) : "memory");
        asm volatile("cp.async.bulk.tensor.2d.global.shared::cta.bulk_group [%0, {%2, %3}], [%1];"
                     ::"l"(&m.ot), "r"(sb + OFF_QT + row * 32), "r"(80 * hg + 64), "r"(128 * r + row) : "memory");
        asm volatile("cp.async.bulk.commit_group;\ncp.async.bulk.wait_group.read 0;" ::: "memory");
      }
      TSM(true, 40 + 4 * wg + w);
      if (ENDBAR) asm volatile("bar.sync 15, 256;" ::: "memory");
    }
  }
}

typedef CUresult (*EncodeFn)(CUtensorMap*, CUtensorMapDataType, cuuint32_t, void*, const cuuint64_t*, const cuuint64_t*,
                             const cuuint32_t*, const cuuint32_t*, CUtensorMapInterleave, CUtensorMapSwizzle,
                             CUtensorMapL2promotion, CUtensorMapFloatOOBfill);

void encode(EncodeFn fn, CUtensorMap* tm, const void* base, int rank, const cuuint64_t* dims, const cuuint64_t* strides,
            const cuuint32_t* box, CUtensorMapSwizzle swz) {
  const cuuint32_t ones[3] = {1, 1, 1};
  fn(tm, CU_TENSOR_MAP_DATA_TYPE_BFLOAT16, rank, const_cast<void*>(base), dims, strides, box, ones,
     CU_TENSOR_MAP_INTERLEAVE_NONE, swz, CU_TENSOR_MAP_L2_PROMOTION_L2_128B, CU_TENSOR_MAP_FLOAT_OOB_FILL_NONE);
}

}

extern "C" void kernel_launch(void* const* d_in, const int* in_sizes, int n_in, void* d_out, int out_size) {
  (void)in_sizes; (void)n_in; (void)out_size;
  Params p;
  p.q = (const __nv_bfloat16*)d_in[0];
  p.k = (const __nv_bfloat16*)d_in[1];
  p.v = (const __nv_bfloat16*)d_in[2];
  p.shift_k = (const __nv_bfloat16*)d_in[3];
  p.ssm_k = (const __nv_bfloat16*)d_in[4];
  p.ssm_D = (const __nv_bfloat16*)d_in[5];
  p.wqkv = (const __nv_bfloat16*)d_in[7];
  p.wo = (const __nv_bfloat16*)d_in[8];
  p.gate_w = (const __nv_bfloat16*)d_in[9];
  p.out = (__nv_bfloat16*)d_out;
  p.zero = 0;

  static EncodeFn fn = nullptr;
  static void *yaddr = nullptr, *uaddr = nullptr;
  if (!fn) {
    cudaDriverEntryPointQueryResult qr;
    void* f = nullptr;
    cudaGetDriverEntryPoint("cuTensorMapEncodeTiled", &f, cudaEnableDefault, &qr);
    fn = (EncodeFn)f;
    cudaGetSymbolAddress(&yaddr, g_Y);
    cudaGetSymbolAddress(&uaddr, g_U);
    cudaFuncSetAttribute(fused_kernel, cudaFuncAttributeMaxDynamicSharedMemorySize, SMEM_BYTES);
  }
  Maps m;
  {
    const cuuint64_t dims[3] = {640, 1024, 2}, st[2] = {2560, 1280};
    const cuuint32_t box[3] = {64, 64, 2};
    encode(fn, &m.x, p.q, 3, dims, st, box, CU_TENSOR_MAP_SWIZZLE_128B);
  }
  {
    const cuuint64_t dims[3] = {640, 640, 3}, st[2] = {3840, 1280};
    const cuuint32_t box[3] = {64, 64, 3}, boxt[3] = {16, 64, 3};
    encode(fn, &m.wm, p.wqkv, 3, dims, st, box, CU_TENSOR_MAP_SWIZZLE_128B);
    encode(fn, &m.wt, p.wqkv, 3, dims, st, boxt, CU_TENSOR_MAP_SWIZZLE_32B);
  }
  {
    const cuuint64_t dims[3] = {64, 2048, 10}, st[2] = {1280, 128};
    const cuuint32_t boxk[3] = {64, 35, 1}, boxv[3] = {64, 32, 1};
    encode(fn, &m.k, p.k, 3, dims, st, boxk, CU_TENSOR_MAP_SWIZZLE_128B);
    encode(fn, &m.v, p.v, 3, dims, st, boxv, CU_TENSOR_MAP_SWIZZLE_128B);
  }
  {
    const cuuint64_t dims[3] = {16, 640, 40}, st[2] = {1280, 32};
    const cuuint32_t box[3] = {16, 40, 5};
    encode(fn, &m.wo, p.wo, 3, dims, st, box, CU_TENSOR_MAP_SWIZZLE_32B);
  }
  {
    const cuuint64_t dims[2] = {2048, 640}, st[1] = {Y_PITCH * 16};
    const cuuint32_t box[2] = {64, 80};
    encode(fn, &m.y, yaddr, 2, dims, st, box, CU_TENSOR_MAP_SWIZZLE_128B);
    const cuuint64_t stu[1] = {U_PITCH * 16};
    const cuuint32_t boxu[2] = {32, 64};
    encode(fn, &m.u, uaddr, 2, dims, stu, boxu, CU_TENSOR_MAP_SWIZZLE_NONE);
  }
  {
    const cuuint64_t dims[2] = {640, 2048}, st[1] = {1280};
    const cuuint32_t bqm[2] = {64, 128}, bqt[2] = {16, 128}, bom[2] = {64, 16}, bot[2] = {16, 16};
    encode(fn, &m.qm, p.q, 2, dims, st, bqm, CU_TENSOR_MAP_SWIZZLE_128B);
    encode(fn, &m.qt, p.q, 2, dims, st, bqt, CU_TENSOR_MAP_SWIZZLE_32B);
    encode(fn, &m.om, p.out, 2, dims, st, bom, CU_TENSOR_MAP_SWIZZLE_128B);
    encode(fn, &m.ot, p.out, 2, dims, st, bot, CU_TENSOR_MAP_SWIZZLE_32B);
  }
  fused_kernel<<<NCTA, NTHR, SMEM_BYTES>>>(m, p);
}
```

```cpp
#include <cuda.h>
#include <cuda_bf16.h>
#include <cuda_runtime.h>
#include <stdint.h>

namespace {

constexpr int SEQ = 2048, DIM = 640, NCTA = 128, NTHR = 512;

#define TRIG_KB 9
#define KV_KB 2
#define DEV_EXIT 0
#define ATT_GATE 1
#define G_AFTER 0
#define FENCE_LO 0
#define FENCE_HI 0
#define PW1 2
#define PW2 1
#define ENDBAR 0
#define PAD_KB 0
#define Y_ALIAS 1
#define H_EARLY 1
#define NOMB 0
#define SRC_ROT 0
#define WAIT_NS 0
#define WB_TRIG B_USIG
#define G_POS 0
#define TAILF 1
#define T_ISSUE 384
#define T_PF 416
#define T_INIT 448
#define ATT_MERGE 0
#define BMAP 1
#define PRE2 1
#define KV_MIX 0
#define O_DEFER 0
#define TASK0 0x52
#define TASK1 0x3
#define TASK2 0x41
#define HALO_FIRST 1
#define PREV_EARLY 0
#define ACQ 0
#define U_TMA 0
#define U_GATE 0
#define RF_GATE 0
#define WO_TRIG B_WST
#define WL_TRIG B_WOP
#define WO_GATE 1

constexpr uint32_t STAGE_BYTES = 47104, ST_W = 16384, ST_WT = 40960;
constexpr uint32_t O_BYTES = 20480, WO_BYTES = 12800;
constexpr uint32_t OFF_OA = 0;
constexpr uint32_t OFF_QS = 3 * O_BYTES, OFF_QT = OFF_QS + 16384;
constexpr uint32_t OFF_WC = 81920;
constexpr uint32_t OFF_WA = 94720;
constexpr uint32_t OFF_GATE = 145920;
constexpr uint32_t OFF_TT = 146432;
constexpr uint32_t OFF_KVX = 148480;
constexpr uint32_t OFF_CH3 = 163840;
constexpr uint32_t CH_BYTES = 12288, U_BYTES = 4096;
constexpr uint32_t OFF_FT = 225280, OFF_GT = 229376;
constexpr uint32_t OFF_CH0 = 188416;
constexpr uint32_t OFF_KVS = OFF_CH0, KVS_V = 4480, KVS_BYTES = 8576;
constexpr uint32_t OFF_WS = OFF_WA;
__device__ __forceinline__ uint32_t off_us(int s) { return OFF_CH0 + 4096 * ((0x65320 >> (4 * s)) & 7); }
constexpr uint32_t OFF_YT = 163840;
constexpr uint32_t OFF_BAR = 231936;
constexpr uint32_t SMEM_BYTES = OFF_BAR + 512;

enum : uint32_t {
  B_FULL1 = 0, B_EMPTY1 = 4, B_S3 = 7, B_FULL2 = 52, B_EMPTY2 = 13, B_U = 8, B_GATE = 12, B_HA = 19, B_HB = 20,
  B_ATTN = 21, B_C34 = 22, B_CONV = 23, B_YFULL = 24, B_EPOCH = 25, B_PREP = 26, B_P1 = 27, B_LAST = 28,
  B_E3 = 29, B_OSIG = 30, B_WOP = 31, B_USIG = 32, B_WST = 33, B_KV = 34, B_KVD = 39, B_QF = 17, B_YST = 40,
  B_US = 45, B_YSIG = 50
};
constexpr uint32_t OFF_EPOCH = OFF_BAR + 8 * 51, OFF_D = OFF_BAR + 8 * 60;
__device__ __forceinline__ uint32_t off_o(int j) { return j < 4 ? OFF_OA + j * O_BYTES : j < 6 ? OFF_CH0 + (j - 4) * O_BYTES : OFF_OA + (j - 6) * O_BYTES; }
__device__ __forceinline__ uint32_t off_w(int j) { return j < 4 ? OFF_WA + j * WO_BYTES : j == 4 ? OFF_KVX : j == 5 ? OFF_WC : OFF_WA + (j - 6) * WO_BYTES; }
__device__ __forceinline__ int step_src(int hg, int j) { return SRC_ROT ? (hg + j) & 7 : j == 0 ? hg : j <= hg ? j - 1 : j; }
__device__ __forceinline__ bool tail_first(int hg) { return TAILF && (hg & 3) == 3; }
__device__ __forceinline__ uint32_t off_ch(int c) { return (c < 3 ? OFF_CH0 : OFF_CH3 - 3 * CH_BYTES) + c * CH_BYTES; }

#define U_PITCH 264
__device__ __align__(1024) uint4 g_U[DIM * U_PITCH];
__device__ uint4 g_O[NCTA * 1280];
#define g_Y g_U
constexpr int Y_PITCH = U_PITCH;
__device__ uint4 g_WO[64 * 800];
__device__ uint4 g_halo[NCTA * 2 * 7 * 32];
__device__ float g_gate[SEQ + PAD_KB * 256];
__device__ unsigned g_cnt[32 * (1 + 2 * 16 + 8 + NCTA)];
constexpr int C_LAUNCH = 0, C_PREP = 32, C_Y = 32 * 17, C_W = 32 * 33, C_O = 32 * 41;

#define TSM(cond, slot) do { } while (0)
#define TSIF(cond, slot) do { if (__LINE__ >= FENCE_LO && __LINE__ < FENCE_HI) sched_fence(); } while (0)
__device__ __forceinline__ void sched_fence() {
  asm volatile("{\n.reg .pred p;\n.reg .u32 c;\nmov.u32 c, %%clock;\nsetp.eq.u32 p, c, 0;\n@p st.shared.u32 [%0], c;\n}"
               ::"r"(1024 + OFF_EPOCH + 4) : "memory");
}
#define TS(slot) TSIF(true, slot)

struct Params {
  const __nv_bfloat16 *q, *k, *v, *shift_k, *ssm_k, *ssm_D, *wqkv, *wo, *gate_w;
  __nv_bfloat16* out;
  uint32_t zero;
};

#define POLL_NS 0
constexpr int SPIN_LIMIT = 1 << 17;

__device__ __forceinline__ void mbar_init(uint32_t bar, uint32_t count) {
  asm volatile("mbarrier.init.shared::cta.b64 [%0], %1;" ::"r"(bar), "r"(count) : "memory");
}
__device__ __forceinline__ void mbar_expect_tx(uint32_t bar, uint32_t bytes) {
  asm volatile("mbarrier.arrive.expect_tx.shared::cta.b64 _, [%0], %1;" ::"r"(bar), "r"(bytes) : "memory");
}
__device__ __forceinline__ void mbar_arrive(uint32_t bar) {
  asm volatile("mbarrier.arrive.shared::cta.b64 _, [%0];" ::"r"(bar) : "memory");
}
__device__ __forceinline__ void mbar_wait(uint32_t bar, uint32_t parity) {
  uint32_t ok;
  int spins = 0;
  do {
    if (WAIT_NS)
      asm volatile("{\n.reg .pred p;\nmbarrier.try_wait.parity.shared::cta.b64 p, [%1], %2, %3;\nselp.b32 %0, 1, 0, p;\n}"
                   : "=r"(ok) : "r"(bar), "r"(parity), "r"(WAIT_NS) : "memory");
    else
      asm volatile("{\n.reg .pred p;\nmbarrier.try_wait.parity.shared::cta.b64 p, [%1], %2;\nselp.b32 %0, 1, 0, p;\n}"
                   : "=r"(ok) : "r"(bar), "r"(parity) : "memory");
    if (++spins > SPIN_LIMIT) break;
  } while (!ok);
}
__device__ __forceinline__ unsigned flag_read(const unsigned* p) {
  unsigned v;
  asm volatile("ld.relaxed.gpu.global.u32 %0, [%1];" : "=r"(v) : "l"(p) : "memory");
  return v;
}
__device__ __forceinline__ void flag_poll(const unsigned* p, unsigned target) {
  unsigned v;
  int spins = 0;
  do {
    if (POLL_NS && spins) __nanosleep(POLL_NS);
    asm volatile("ld.relaxed.gpu.global.u32 %0, [%1];" : "=r"(v) : "l"(p) : "memory");
    if (++spins > SPIN_LIMIT) break;
  } while ((int)(v - target) < 0);
}
__device__ __forceinline__ void flag_wait(const unsigned* p, unsigned target) {
  flag_poll(p, target);
  if (ACQ) asm volatile("fence.acquire.gpu;\nfence.proxy.async.global;" ::: "memory");
}
__device__ __forceinline__ void flag_signal(unsigned* p, int n, int lane) {
  if (lane == 0) asm volatile("fence.release.gpu;" ::: "memory");
  __syncwarp();
  if (lane < n) asm volatile("red.relaxed.gpu.global.add.u32 [%0], 1;" ::"l"(p + 32 * lane) : "memory");
}
__device__ __forceinline__ void flag_bump(unsigned* p) {
  asm volatile("red.relaxed.gpu.global.add.u32 [%0], 1;" ::"l"(p) : "memory");
}
__device__ __forceinline__ void fence_async_smem() { asm volatile("fence.proxy.async.shared::cta;" ::: "memory"); }
__device__ __forceinline__ void wg_sync(int id) { asm volatile("bar.sync %0, 128;" ::"r"(id) : "memory"); }

__device__ __forceinline__ void tma_2d(uint32_t dst, const CUtensorMap* tm, int c0, int c1, uint32_t bar) {
  asm volatile("cp.async.bulk.tensor.2d.shared::cluster.global.mbarrier::complete_tx::bytes [%0], [%1, {%3, %4}], [%2];"
               ::"r"(dst), "l"(tm), "r"(bar), "r"(c0), "r"(c1) : "memory");
}
__device__ __forceinline__ void tma_3d(uint32_t dst, const CUtensorMap* tm, int c0, int c1, int c2, uint32_t bar) {
  asm volatile("cp.async.bulk.tensor.3d.shared::cluster.global.mbarrier::complete_tx::bytes [%0], [%1, {%3, %4, %5}], [%2];"
               ::"r"(dst), "l"(tm), "r"(bar), "r"(c0), "r"(c1), "r"(c2) : "memory");
}
__device__ __forceinline__ void bulk_load(uint32_t dst, const void* src, uint32_t bytes, uint32_t bar) {
  asm volatile("cp.async.bulk.shared::cluster.global.mbarrier::complete_tx::bytes [%0], [%1], %2, [%3];"
               ::"r"(dst), "l"(src), "r"(bytes), "r"(bar) : "memory");
}
__device__ __forceinline__ void tm_prefetch(const CUtensorMap* tm) {
  asm volatile("prefetch.tensormap [%0];" ::"l"(tm) : "memory");
}

__device__ __forceinline__ void wg_fence() { asm volatile("wgmma.fence.sync.aligned;" ::: "memory"); }
__device__ __forceinline__ void wg_commit() { asm volatile("wgmma.commit_group.sync.aligned;" ::: "memory"); }
template <int N> __device__ __forceinline__ void wg_wait() { asm volatile("wgmma.wait_group.sync.aligned %0;" ::"n"(N) : "memory"); }
__device__ __forceinline__ uint32_t desc_lo(uint32_t addr, uint32_t lbo) { return ((addr & 0x3FFFF) >> 4) | ((lbo >> 4) << 16); }
constexpr uint32_t desc_hi(uint32_t sbo, uint32_t swz) { return (sbo >> 4) | (swz << 30); }
constexpr uint32_t HI_SW128 = desc_hi(1024, 1), HI_SW64 = desc_hi(512, 2), HI_SW32 = desc_hi(256, 3), HI_NONE = desc_hi(128, 0);
template <int N> __device__ __forceinline__ void pin(float* d) {
#pragma unroll
  for (int i = 0; i < N; i++) asm volatile("" : "+f"(d[i])::"memory");
}

__device__ __forceinline__ uint32_t lds32(uint32_t a) {
  uint32_t v;
  asm volatile("ld.volatile.shared.u32 %0, [%1];" : "=r"(v) : "r"(a) : "memory");
  return v;
}
__device__ __forceinline__ uint4 ldg128(const void* a) {
  uint4 v;
  asm volatile("ld.global.nc.v4.u32 {%0, %1, %2, %3}, [%4];" : "=r"(v.x), "=r"(v.y), "=r"(v.z), "=r"(v.w) : "l"(a) : "memory");
  return v;
}
__device__ __forceinline__ uint2 ldg64(const void* a) {
  uint2 v;
  asm volatile("ld.global.nc.v2.u32 {%0, %1}, [%2];" : "=r"(v.x), "=r"(v.y) : "l"(a) : "memory");
  return v;
}
__device__ __forceinline__ void ldsm4(uint32_t* r, uint32_t a) {
  asm volatile("ldmatrix.sync.aligned.m8n8.x4.shared.b16 {%0, %1, %2, %3}, [%4];"
               : "=r"(r[0]), "=r"(r[1]), "=r"(r[2]), "=r"(r[3]) : "r"(a) : "memory");
}
__device__ __forceinline__ void ldsm4t(uint32_t* r, uint32_t a) {
  asm volatile("ldmatrix.sync.aligned.m8n8.x4.trans.shared.b16 {%0, %1, %2, %3}, [%4];"
               : "=r"(r[0]), "=r"(r[1]), "=r"(r[2]), "=r"(r[3]) : "r"(a) : "memory");
}
__device__ __forceinline__ uint4 lds128(uint32_t a) {
  uint4 v;
  asm volatile("ld.shared.v4.u32 {%0, %1, %2, %3}, [%4];" : "=r"(v.x), "=r"(v.y), "=r"(v.z), "=r"(v.w) : "r"(a) : "memory");
  return v;
}
__device__ __forceinline__ void sts128(uint32_t a, uint32_t x, uint32_t y, uint32_t z, uint32_t w) {
  asm volatile("st.shared.v4.u32 [%0], {%1, %2, %3, %4};" ::"r"(a), "r"(x), "r"(y), "r"(z), "r"(w) : "memory");
}
__device__ __forceinline__ void stsm4(uint32_t a, const uint32_t* r) {
  asm volatile("stmatrix.sync.aligned.m8n8.x4.shared.b16 [%0], {%1, %2, %3, %4};" ::"r"(a), "r"(r[0]), "r"(r[1]), "r"(r[2]), "r"(r[3]) : "memory");
}
__device__ __forceinline__ void stsm4t(uint32_t a, const uint32_t* r) {
  asm volatile("stmatrix.sync.aligned.m8n8.x4.trans.shared.b16 [%0], {%1, %2, %3, %4};" ::"r"(a), "r"(r[0]), "r"(r[1]), "r"(r[2]), "r"(r[3]) : "memory");
}
__device__ __forceinline__ uint32_t pack2(float lo, float hi) {
  uint32_t r;
  asm("cvt.rn.bf16x2.f32 %0, %1, %2;" : "=r"(r) : "f"(hi), "f"(lo));
  return r;
}
__device__ __forceinline__ uint32_t movm(uint32_t a) {
  uint32_t d;
  asm volatile("movmatrix.sync.aligned.m8n8.trans.b16 %0, %1;" : "=r"(d) : "r"(a));
  return d;
}
__device__ __forceinline__ uint32_t bmul(uint32_t a, uint32_t b) {
  uint32_t d;
  asm("mul.rn.bf16x2 %0, %1, %2;" : "=r"(d) : "r"(a), "r"(b));
  return d;
}
__device__ __forceinline__ uint32_t badd(uint32_t a, uint32_t b) {
  uint32_t d;
  asm("add.rn.bf16x2 %0, %1, %2;" : "=r"(d) : "r"(a), "r"(b));
  return d;
}
__device__ __forceinline__ float bf_lo(uint32_t x) { return __uint_as_float(x << 16); }
__device__ __forceinline__ float bf_hi(uint32_t x) { return __uint_as_float(x & 0xFFFF0000u); }
__device__ __forceinline__ float ex2(float x) {
  float y;
  asm("ex2.approx.ftz.f32 %0, %1;" : "=f"(y) : "f"(x));
  return y;
}
__device__ __forceinline__ float rcp(float x) {
  float y;
  asm("rcp.approx.ftz.f32 %0, %1;" : "=f"(y) : "f"(x));
  return y;
}
__device__ __forceinline__ void mma16816(float* d, uint32_t a0, uint32_t a1, uint32_t a2, uint32_t a3, uint32_t b0, uint32_t b1) {
  asm volatile("mma.sync.aligned.m16n8k16.row.col.f32.bf16.bf16.f32 {%0, %1, %2, %3}, {%4, %5, %6, %7}, {%8, %9}, {%0, %1, %2, %3};"
               : "+f"(d[0]), "+f"(d[1]), "+f"(d[2]), "+f"(d[3])
               : "r"(a0), "r"(a1), "r"(a2), "r"(a3), "r"(b0), "r"(b1));
}
__device__ __forceinline__ void mma1688(float* d, uint32_t a0, uint32_t a1, uint32_t b0) {
  asm volatile("mma.sync.aligned.m16n8k8.row.col.f32.bf16.bf16.f32 {%0, %1, %2, %3}, {%4, %5}, {%6}, {%0, %1, %2, %3};"
               : "+f"(d[0]), "+f"(d[1]), "+f"(d[2]), "+f"(d[3])
               : "r"(a0), "r"(a1), "r"(b0));
}

template <int N> struct WgRS;
template <int N> struct WgSST;
template <> struct WgRS<32> {
  template <uint32_t HB>
  static __device__ __forceinline__ void mma(float* d, const uint32_t* a, uint32_t db) {
    asm volatile("{\n.reg .pred p;\n.reg .b64 db;\nsetp.ne.b32 p, %22, 0;\n"
      "mov.b64 db, {%20, %21};\n"
      "wgmma.mma_async.sync.aligned.m64n32k16.f32.bf16.bf16 {"
      "%0, %1, %2, %3, %4, %5, %6, %7, %8, %9, %10, %11, %12, %13, %14, %15"
      "}, {%16, %17, %18, %19}, db, p, 1, 1, 1;\n}\n"
      : "+f"(d[0]), "+f"(d[1]), "+f"(d[2]), "+f"(d[3]), "+f"(d[4]), "+f"(d[5]), "+f"(d[6]), "+f"(d[7]),
        "+f"(d[8]), "+f"(d[9]), "+f"(d[10]), "+f"(d[11]), "+f"(d[12]), "+f"(d[13]), "+f"(d[14]), "+f"(d[15])
      : "r"(a[0]), "r"(a[1]), "r"(a[2]), "r"(a[3]), "r"(db), "n"(HB), "n"(1));
  }
  template <uint32_t HB>
  static __device__ __forceinline__ void set(float* d, const uint32_t* a, uint32_t db) {
    asm volatile("{\n.reg .pred p;\n.reg .b64 db;\nsetp.ne.b32 p, %22, 0;\n"
      "mov.b64 db, {%20, %21};\n"
      "wgmma.mma_async.sync.aligned.m64n32k16.f32.bf16.bf16 {"
      "%0, %1, %2, %3, %4, %5, %6, %7, %8, %9, %10, %11, %12, %13, %14, %15"
      "}, {%16, %17, %18, %19}, db, p, 1, 1, 1;\n}\n"
      : "=f"(d[0]), "=f"(d[1]), "=f"(d[2]), "=f"(d[3]), "=f"(d[4]), "=f"(d[5]), "=f"(d[6]), "=f"(d[7]),
        "=f"(d[8]), "=f"(d[9]), "=f"(d[10]), "=f"(d[11]), "=f"(d[12]), "=f"(d[13]), "=f"(d[14]), "=f"(d[15])
      : "r"(a[0]), "r"(a[1]), "r"(a[2]), "r"(a[3]), "r"(db), "n"(HB), "n"(0));
  }
};
template <> struct WgRS<64> {
  template <uint32_t HB>
  static __device__ __forceinline__ void mma(float* d, const uint32_t* a, uint32_t db) {
    asm volatile("{\n.reg .pred p;\n.reg .b64 db;\nsetp.ne.b32 p, %38, 0;\n"
      "mov.b64 db, {%36, %37};\n"
      "wgmma.mma_async.sync.aligned.m64n64k16.f32.bf16.bf16 {"
      "%0, %1, %2, %3, %4, %5, %6, %7, %8, %9, %10, %11, %12, %13, %14, %15, "
      "%16, %17, %18, %19, %20, %21, %22, %23, %24, %25, %26, %27, %28, %29, %30, %31"
      "}, {%32, %33, %34, %35}, db, p, 1, 1, 1;\n}\n"
      : "+f"(d[0]), "+f"(d[1]), "+f"(d[2]), "+f"(d[3]), "+f"(d[4]), "+f"(d[5]), "+f"(d[6]), "+f"(d[7]),
        "+f"(d[8]), "+f"(d[9]), "+f"(d[10]), "+f"(d[11]), "+f"(d[12]), "+f"(d[13]), "+f"(d[14]), "+f"(d[15]),
        "+f"(d[16]), "+f"(d[17]), "+f"(d[18]), "+f"(d[19]), "+f"(d[20]), "+f"(d[21]), "+f"(d[22]), "+f"(d[23]),
        "+f"(d[24]), "+f"(d[25]), "+f"(d[26]), "+f"(d[27]), "+f"(d[28]), "+f"(d[29]), "+f"(d[30]), "+f"(d[31])
      : "r"(a[0]), "r"(a[1]), "r"(a[2]), "r"(a[3]), "r"(db), "n"(HB), "n"(1));
  }
  template <uint32_t HB>
  static __device__ __forceinline__ void set(float* d, const uint32_t* a, uint32_t db) {
    asm volatile("{\n.reg .pred p;\n.reg .b64 db;\nsetp.ne.b32 p, %38, 0;\n"
      "mov.b64 db, {%36, %37};\n"
      "wgmma.mma_async.sync.aligned.m64n64k16.f32.bf16.bf16 {"
      "%0, %1, %2, %3, %4, %5, %6, %7, %8, %9, %10, %11, %12, %13, %14, %15, "
      "%16, %17, %18, %19, %20, %21, %22, %23, %24, %25, %26, %27, %28, %29, %30, %31"
      "}, {%32, %33, %34, %35}, db, p, 1, 1, 1;\n}\n"
      : "=f"(d[0]), "=f"(d[1]), "=f"(d[2]), "=f"(d[3]), "=f"(d[4]), "=f"(d[5]), "=f"(d[6]), "=f"(d[7]),
        "=f"(d[8]), "=f"(d[9]), "=f"(d[10]), "=f"(d[11]), "=f"(d[12]), "=f"(d[13]), "=f"(d[14]), "=f"(d[15]),
        "=f"(d[16]), "=f"(d[17]), "=f"(d[18]), "=f"(d[19]), "=f"(d[20]), "=f"(d[21]), "=f"(d[22]), "=f"(d[23]),
        "=f"(d[24]), "=f"(d[25]), "=f"(d[26]), "=f"(d[27]), "=f"(d[28]), "=f"(d[29]), "=f"(d[30]), "=f"(d[31])
      : "r"(a[0]), "r"(a[1]), "r"(a[2]), "r"(a[3]), "r"(db), "n"(HB), "n"(0));
  }
};
template <> struct WgSST<48> {
  template <uint32_t HA, uint32_t HB>
  static __device__ __forceinline__ void mma(float* d, uint32_t da, uint32_t db, int sc) {
    asm volatile("{\n.reg .pred p;\n.reg .b64 da, db;\nsetp.ne.b32 p, %28, 0;\n"
      "mov.b64 da, {%24, %25};\nmov.b64 db, {%26, %27};\n"
      "wgmma.mma_async.sync.aligned.m64n48k16.f32.bf16.bf16 {"
      "%0, %1, %2, %3, %4, %5, %6, %7, %8, %9, %10, %11, %12, %13, %14, %15, "
      "%16, %17, %18, %19, %20, %21, %22, %23"
      "}, da, db, p, 1, 1, 0, 1;\n}\n"
      : "+f"(d[0]), "+f"(d[1]), "+f"(d[2]), "+f"(d[3]), "+f"(d[4]), "+f"(d[5]), "+f"(d[6]), "+f"(d[7]),
        "+f"(d[8]), "+f"(d[9]), "+f"(d[10]), "+f"(d[11]), "+f"(d[12]), "+f"(d[13]), "+f"(d[14]), "+f"(d[15]),
        "+f"(d[16]), "+f"(d[17]), "+f"(d[18]), "+f"(d[19]), "+f"(d[20]), "+f"(d[21]), "+f"(d[22]), "+f"(d[23])
      : "r"(da), "n"(HA), "r"(db), "n"(HB), "r"(sc));
  }
};
template <> struct WgSST<80> {
  template <uint32_t HA, uint32_t HB>
  static __device__ __forceinline__ void mma(float* d, uint32_t da, uint32_t db, int sc) {
    asm volatile("{\n.reg .pred p;\n.reg .b64 da, db;\nsetp.ne.b32 p, %44, 0;\n"
      "mov.b64 da, {%40, %41};\nmov.b64 db, {%42, %43};\n"
      "wgmma.mma_async.sync.aligned.m64n80k16.f32.bf16.bf16 {"
      "%0, %1, %2, %3, %4, %5, %6, %7, %8, %9, %10, %11, %12, %13, %14, %15, "
      "%16, %17, %18, %19, %20, %21, %22, %23, %24, %25, %26, %27, %28, %29, %30, %31, "
      "%32, %33, %34, %35, %36, %37, %38, %39"
      "}, da, db, p, 1, 1, 0, 1;\n}\n"
      : "+f"(d[0]), "+f"(d[1]), "+f"(d[2]), "+f"(d[3]), "+f"(d[4]), "+f"(d[5]), "+f"(d[6]), "+f"(d[7]),
        "+f"(d[8]), "+f"(d[9]), "+f"(d[10]), "+f"(d[11]), "+f"(d[12]), "+f"(d[13]), "+f"(d[14]), "+f"(d[15]),
        "+f"(d[16]), "+f"(d[17]), "+f"(d[18]), "+f"(d[19]), "+f"(d[20]), "+f"(d[21]), "+f"(d[22]), "+f"(d[23]),
        "+f"(d[24]), "+f"(d[25]), "+f"(d[26]), "+f"(d[27]), "+f"(d[28]), "+f"(d[29]), "+f"(d[30]), "+f"(d[31]),
        "+f"(d[32]), "+f"(d[33]), "+f"(d[34]), "+f"(d[35]), "+f"(d[36]), "+f"(d[37]), "+f"(d[38]), "+f"(d[39])
      : "r"(da), "n"(HA), "r"(db), "n"(HB), "r"(sc));
  }
};
template <> struct WgSST<192> {
  template <uint32_t HA, uint32_t HB>
  static __device__ __forceinline__ void mma(float* d, uint32_t da, uint32_t db, int sc) {
    asm volatile("{\n.reg .pred p;\n.reg .b64 da, db;\nsetp.ne.b32 p, %100, 0;\n"
      "mov.b64 da, {%96, %97};\nmov.b64 db, {%98, %99};\n"
      "wgmma.mma_async.sync.aligned.m64n192k16.f32.bf16.bf16 {"
      "%0, %1, %2, %3, %4, %5, %6, %7, %8, %9, %10, %11, %12, %13, %14, %15, "
      "%16, %17, %18, %19, %20, %21, %22, %23, %24, %25, %26, %27, %28, %29, %30, %31, "
      "%32, %33, %34, %35, %36, %37, %38, %39, %40, %41, %42, %43, %44, %45, %46, %47, "
      "%48, %49, %50, %51, %52, %53, %54, %55, %56, %57, %58, %59, %60, %61, %62, %63, "
      "%64, %65, %66, %67, %68, %69, %70, %71, %72, %73, %74, %75, %76, %77, %78, %79, "
      "%80, %81, %82, %83, %84, %85, %86, %87, %88, %89, %90, %91, %92, %93, %94, %95"
      "}, da, db, p, 1, 1, 0, 1;\n}\n"
      : "+f"(d[0]), "+f"(d[1]), "+f"(d[2]), "+f"(d[3]), "+f"(d[4]), "+f"(d[5]), "+f"(d[6]), "+f"(d[7]),
        "+f"(d[8]), "+f"(d[9]), "+f"(d[10]), "+f"(d[11]), "+f"(d[12]), "+f"(d[13]), "+f"(d[14]), "+f"(d[15]),
        "+f"(d[16]), "+f"(d[17]), "+f"(d[18]), "+f"(d[19]), "+f"(d[20]), "+f"(d[21]), "+f"(d[22]), "+f"(d[23]),
        "+f"(d[24]), "+f"(d[25]), "+f"(d[26]), "+f"(d[27]), "+f"(d[28]), "+f"(d[29]), "+f"(d[30]), "+f"(d[31]),
        "+f"(d[32]), "+f"(d[33]), "+f"(d[34]), "+f"(d[35]), "+f"(d[36]), "+f"(d[37]), "+f"(d[38]), "+f"(d[39]),
        "+f"(d[40]), "+f"(d[41]), "+f"(d[42]), "+f"(d[43]), "+f"(d[44]), "+f"(d[45]), "+f"(d[46]), "+f"(d[47]),
        "+f"(d[48]), "+f"(d[49]), "+f"(d[50]), "+f"(d[51]), "+f"(d[52]), "+f"(d[53]), "+f"(d[54]), "+f"(d[55]),
        "+f"(d[56]), "+f"(d[57]), "+f"(d[58]), "+f"(d[59]), "+f"(d[60]), "+f"(d[61]), "+f"(d[62]), "+f"(d[63]),
        "+f"(d[64]), "+f"(d[65]), "+f"(d[66]), "+f"(d[67]), "+f"(d[68]), "+f"(d[69]), "+f"(d[70]), "+f"(d[71]),
        "+f"(d[72]), "+f"(d[73]), "+f"(d[74]), "+f"(d[75]), "+f"(d[76]), "+f"(d[77]), "+f"(d[78]), "+f"(d[79]),
        "+f"(d[80]), "+f"(d[81]), "+f"(d[82]), "+f"(d[83]), "+f"(d[84]), "+f"(d[85]), "+f"(d[86]), "+f"(d[87]),
        "+f"(d[88]), "+f"(d[89]), "+f"(d[90]), "+f"(d[91]), "+f"(d[92]), "+f"(d[93]), "+f"(d[94]), "+f"(d[95])
      : "r"(da), "n"(HA), "r"(db), "n"(HB), "r"(sc));
  }
};

struct FftConst {
  uint32_t f[2][4], fi[4][4];
  float ta[4], tb[4];
};
__device__ __forceinline__ void cis(int m, float scale, float& c, float& s) {
  const float a = (float)m * (-6.283185307179586f * scale);
  c = __cosf(a);
  s = __sinf(a);
}
__device__ __forceinline__ void fft_tables(uint32_t (&v)[12], int tw) {
  const int row = tw >> 2, ch = tw & 3;
#pragma unroll
  for (int i = 0; i < 4; i++) {
    float c[2], s[2], x[2];
#pragma unroll
    for (int e = 0; e < 2; e++) {
      cis((((32 * (8 * ch + 2 * i + e) + 15) * (4 * row - 63) + 2048) & 4095) - 2048, 1.f / 4096, c[e], s[e]);
      float gc, gs;
      cis((((row & 15) * (8 * (ch & 1) + 2 * i + e) + 8) & 15) - 8, 1.f / 16, gc, gs);
      x[e] = (row >> 4) == (ch >> 1) ? gc : (ch >> 1) ? gs : -gs;
    }
    v[i] = pack2(c[0] * 0.125f, c[1] * 0.125f);
    v[4 + i] = pack2(s[0] * 0.125f, s[1] * 0.125f);
    v[8 + i] = pack2(x[0], x[1]);
  }
#pragma unroll
  for (int i = 0; i < 12; i++) asm volatile("" : "+r"(v[i]));
}
__device__ __forceinline__ void fft_tables_store(const uint32_t (&v)[12], uint32_t sb, int tw) {
  const int row = tw >> 2;
  const uint32_t x = ((tw ^ (row >> 1)) & 3) << 4, a = sb + OFF_FT + (16 * (row >> 3) + (row & 7)) * 64 + x;
  sts128(a, v[0], v[1], v[2], v[3]);
  sts128(a + 512, v[4], v[5], v[6], v[7]);
  sts128(sb + OFF_GT + row * 64 + x, v[8], v[9], v[10], v[11]);
}
__device__ __forceinline__ void fft_twiddles(float (&v)[4], int tw) {
#pragma unroll
  for (int i = 0; i < 2; i++) {
    float c, s;
    cis((2 * (2 * (tw & 3) + i) - 15) * (4 * (tw >> 2) - 63), 1.f / 4096, c, s);
    v[2 * i] = __fdividef(-s, 1.f + c);
    v[2 * i + 1] = s;
  }
  pin<4>(v);
}
__device__ __forceinline__ void fft_matrices(FftConst& k, uint32_t sb, int w, int lane) {
  const uint32_t x = (lane >> 1) & 3;
  const uint4 t0 = lds128(sb + OFF_TT + 512 * w + 16 * lane), t1 = lds128(sb + OFF_TT + 512 * w + 16 * (lane ^ 3));
  k.ta[0] = __uint_as_float(t0.x); k.tb[0] = __uint_as_float(t0.y); k.ta[1] = __uint_as_float(t0.z); k.tb[1] = __uint_as_float(t0.w);
  k.ta[3] = __uint_as_float(t1.x); k.tb[3] = __uint_as_float(t1.y); k.ta[2] = __uint_as_float(t1.z); k.tb[2] = __uint_as_float(t1.w);
#pragma unroll
  for (int i = 0; i < 2; i++) {
    ldsm4(k.f[i], sb + OFF_FT + (16 * w + (lane & 15)) * 64 + (((2 * i + (lane >> 4)) ^ x) << 4));
    ldsm4t(k.fi[i], sb + OFF_FT + (32 * i + lane) * 64 + ((w ^ x) << 4));
#pragma unroll
    for (int j = 0; j < 4; j++) {
      k.fi[2 + i][j] = (j & 1) ? k.fi[i][j - 1] ^ 0x80008000u : k.fi[i][j + 1];
      asm volatile("" : "+r"(k.fi[2 + i][j]));
    }
  }
}
__device__ __forceinline__ void rot(bool inv, float& x, float& y, float a, float b) {
  x = fmaf(inv ? -a : a, y, x);
  y = fmaf(inv ? -b : b, x, y);
  x = fmaf(inv ? -a : a, y, x);
}
__device__ __forceinline__ void twiddle_fwd(uint32_t (&a)[4][4], float* d, const FftConst& k) {
#pragma unroll
  for (int q = 0; q < 4; q++)
#pragma unroll
    for (int j = 0; j < 2; j++) {
      float* x = d + 8 * q + 4 * j;
      rot(j, x[0], x[2], k.ta[2 * j], k.tb[2 * j]);
      rot(j, x[1], x[3], k.ta[2 * j + 1], k.tb[2 * j + 1]);
      a[q & 2][2 * j + (q & 1)] = pack2(x[0], x[1]);
      a[(q & 2) + 1][2 * j + (q & 1)] = pack2(x[2], x[3]);
    }
}
__device__ __forceinline__ void g_step(float* d, const uint32_t (&a)[4][4], uint32_t dre, uint32_t dim) {
  WgRS<32>::set<HI_SW64>(d, a[0], dre);
  WgRS<32>::set<HI_SW64>(d + 16, a[2], dre);
  WgRS<32>::mma<HI_SW64>(d, a[1], dim);
  WgRS<32>::mma<HI_SW64>(d + 16, a[3], dim);
  wg_commit();
}

__device__ __forceinline__ void conv_channel(const FftConst& k, uint32_t sb, int c, int wg, int w, int lane) {
  const uint32_t cb = sb + off_ch(c), bars = sb + OFF_BAR;
  const uint32_t du = desc_lo(cb, 1024), dg = desc_lo(sb + OFF_GT, 16), dz = desc_lo(cb + U_BYTES, 16);
  float U[32], H[32];
  uint32_t a[4][4], e[4][4];
  const float dv = __uint_as_float(lds32(sb + OFF_D + 4 * c));
  wg_fence();
  WgRS<64>::set<HI_SW32>(H, k.f[0], du + 256);
  WgRS<64>::mma<HI_SW32>(H, k.f[1], du + 256 + 32);
  wg_commit();
  wg_wait<0>();
  pin<32>(H);
  twiddle_fwd(a, H, k);
  if (ATT_GATE && H_EARLY) mbar_wait(bars + 8 * B_ATTN, 0);
  mbar_wait(bars + 8 * (B_U + (c < 3 ? c : 3)), 0);
  TSM(w == 0 && c < 3, 7 + wg);
  wg_fence();
  WgRS<64>::set<HI_SW32>(U, k.f[0], du);
  WgRS<64>::mma<HI_SW32>(U, k.f[1], du + 32);
  wg_commit();
  g_step(H, a, dg, dg + 64);
  wg_wait<1>();
  pin<32>(U);
  twiddle_fwd(e, U, k);
  wg_fence();
  g_step(U, e, dg, dg + 64);
  wg_wait<0>();
  pin<32>(U);
  pin<32>(H);
#pragma unroll
  for (int j = 0; j < 2; j++) {
    float pr[4][2], pi[4][2];
#pragma unroll
    for (int x = 0; x < 2; x++) {
      H[4 * j + x] += dv;
#pragma unroll
      for (int m = 0; m < 4; m++) {
#pragma unroll
        for (int q = 0; q <= m; q++) {
          const int ih = 16 * (q >> 1) + 2 * (q & 1) + 4 * j + x, iu = 16 * ((m - q) >> 1) + 2 * ((m - q) & 1) + 4 * j + x;
          pr[m][x] = q ? fmaf(H[ih], U[iu], pr[m][x]) : H[ih] * U[iu];
          pi[m][x] = q ? fmaf(H[ih], U[iu + 8], pi[m][x]) : H[ih] * U[iu + 8];
          pr[m][x] = fmaf(-H[ih + 8], U[iu + 8], pr[m][x]);
          pi[m][x] = fmaf(H[ih + 8], U[iu], pi[m][x]);
        }
      }
    }
#pragma unroll
    for (int m = 0; m < 4; m++) {
      a[m & 2][2 * j + (m & 1)] = pack2(pr[m][0], pr[m][1]);
      a[(m & 2) + 1][2 * j + (m & 1)] = pack2(pi[m][0], pi[m][1]);
    }
  }
  wg_fence();
  g_step(U, a, dg + 64, dg);
  const uint32_t za = cb + U_BYTES + (8 * w + (lane & 7)) * 128 + (((lane >> 3) ^ (lane & 7)) << 4);
  const uint32_t ya = cb + (lane >> 4) * 1024 + (8 * w + (lane & 7)) * 32 + ((((lane >> 3) ^ (lane >> 2)) & 1) << 4);
  wg_sync(1 + wg);
  wg_wait<0>();
  pin<32>(U);
  TSIF(w == 0, 80 + c);
#pragma unroll
  for (int p = 0; p < 2; p++) {
#pragma unroll
    for (int i = 0; i < 4; i++) {
      const int j = i & 1;
      float* x = U + 16 * p + 4 * j + (i & 2);
      rot(!j, x[8], x[0], k.ta[2 * j], k.tb[2 * j]);
      rot(!j, x[9], x[1], k.ta[2 * j + 1], k.tb[2 * j + 1]);
      e[p][i] = pack2(x[8], x[9]);
      e[2 + p][i] = pack2(x[0], x[1]);
    }
    stsm4(za ^ (64 * p), e[p]);
    stsm4((za ^ (64 * p)) + 4096, e[2 + p]);
  }
  fence_async_smem();
  wg_sync(1 + wg);
  wg_fence();
  WgRS<64>::set<HI_SW128>(H, k.fi[0], dz);
#pragma unroll
  for (int ks = 1; ks < 4; ks++) WgRS<64>::mma<HI_SW128>(H, k.fi[ks], dz + 128 * ks);
  wg_commit();
  wg_wait<0>();
  pin<32>(H);
  TSIF(w == 0, 88 + c);
#pragma unroll
  for (int j = 0; j < 8; j++)
    a[j >> 2][j & 3] = j < 2 ? pack2(H[4 * j], H[4 * j + 1]) : pack2(H[4 * j] + H[4 * j - 6], H[4 * j + 1] + H[4 * j - 5]);
  stsm4(ya, a[0]);
  stsm4(ya + 2048, a[1]);
  fence_async_smem();
  __syncwarp();
}

__device__ __forceinline__ void prep_slab(uint4* res, const uint2* sw, uint32_t sb, int slab, int w, int lane) {
  const int t = lane & 3, tp = (lane & 7) >> 1, pos = 8 * tp + 2 * (((lane >> 3) + tp) & 3) + (lane & 1);
  const uint32_t base = sb + OFF_KVS + slab * KVS_BYTES + pos * 128;
  uint32_t kk[2][4][4], vv[2][4];
  mbar_wait(sb + OFF_BAR + 8 * (B_KV + slab), 0);
#pragma unroll
  for (int h = 0; h < 2; h++) {
#pragma unroll
    for (int j = 0; j < 4; j++) {
      const uint32_t a = base + 128 * j;
      ldsm4t(kk[h][j], a + (((w + 4 * h) ^ ((a >> 7) & 7)) << 4));
    }
    const uint32_t a = base + KVS_V;
    ldsm4t(vv[h], a + (((w + 4 * h) ^ ((a >> 7) & 7)) << 4));
  }
#pragma unroll
  for (int h = 0; h < 2; h++) {
    uint32_t (&k)[4][4] = kk[h];
    uint32_t (&v)[4] = vv[h];
    const uint32_t w0 = __byte_perm(sw[h].x, 0, 0x1010), w1 = __byte_perm(sw[h].x, 0, 0x3232);
    const uint32_t w2 = __byte_perm(sw[h].y, 0, 0x1010), w3 = __byte_perm(sw[h].y, 0, 0x3232);
#pragma unroll
    for (int m = 0; m < 4; m++)
      v[m] = bmul(badd(badd(badd(bmul(k[0][m], w3), bmul(k[1][m], w2)), bmul(k[2][m], w1)), bmul(k[3][m], w0)), v[m]);
    uint32_t a[4];
#pragma unroll
    for (int m = 0; m < 4; m++) a[m] = (t & 1) ? v[(m + 3) & 3] : v[m];
    res[h] = (t & 2) ? make_uint4(a[2], a[3], a[0], a[1]) : make_uint4(a[0], a[1], a[2], a[3]);
  }
}

__device__ __forceinline__ void prep_gate(const Params& p, int b, int w, int lane) {
  uint2 gw[5], x[4][5];
#pragma unroll
  for (int j = 0; j < 5; j++) gw[j] = ldg64(reinterpret_cast<const uint2*>(p.gate_w) + lane + 32 * j);
#pragma unroll
  for (int i = 0; i < 4; i++)
#pragma unroll
    for (int j = 0; j < 5; j++)
      x[i][j] = ldg64(reinterpret_cast<const uint2*>(p.q) + (16 * b + 4 * w + i) * (DIM / 4) + lane + 32 * j);
  float s[4];
#pragma unroll
  for (int i = 0; i < 4; i++) {
    s[i] = 0.f;
#pragma unroll
    for (int j = 0; j < 5; j++) {
      const uint32_t m0 = bmul(x[i][j].x, gw[j].x), m1 = bmul(x[i][j].y, gw[j].y);
      s[i] += (bf_lo(m0) + bf_hi(m0)) + (bf_lo(m1) + bf_hi(m1));
    }
  }
  const bool h = lane & 16, q = lane & 8;
  const float a = (h ? s[2] : s[0]) + __shfl_xor_sync(0xffffffffu, h ? s[0] : s[2], 16);
  const float c = (h ? s[3] : s[1]) + __shfl_xor_sync(0xffffffffu, h ? s[1] : s[3], 16);
  float z = (q ? c : a) + __shfl_xor_sync(0xffffffffu, q ? a : c, 8);
#pragma unroll
  for (int o = 4; o > 0; o >>= 1) z += __shfl_xor_sync(0xffffffffu, z, o);
  z = bf_lo(pack2(z, 0.f));
  if ((lane & 7) == 0) g_gate[16 * b + 4 * w + (lane >> 3)] = bf_lo(pack2(__fdividef(1.f, 1.f + __expf(-z)), 0.f));
}

__device__ __forceinline__ uint32_t bmax(uint32_t a, uint32_t b) {
  uint32_t d;
  asm("max.bf16x2 %0, %1, %2;" : "=r"(d) : "r"(a), "r"(b));
  return d;
}
__device__ __forceinline__ void softmax_two(const float (&l)[2][2], uint32_t& p0, uint32_t& p1) {
  constexpr float kScale = 0.22360679774997896f, kLog2e = 1.4426950408889634f;
  const uint32_t r0 = pack2(l[0][0], l[1][0]), r1 = pack2(l[0][1], l[1][1]);
  const uint32_t x0 = pack2(bf_lo(r0) * kScale, bf_hi(r0) * kScale), x1 = pack2(bf_lo(r1) * kScale, bf_hi(r1) * kScale);
  uint32_t m = bmax(x0, x1);
  m = bmax(m, __shfl_xor_sync(0xffffffffu, m, 1));
  m = bmax(m, __shfl_xor_sync(0xffffffffu, m, 2));
  const float m0 = bf_lo(m) * kLog2e, m1 = bf_hi(m) * kLog2e;
  p0 = pack2(ex2(bf_lo(x0) * kLog2e - m0), ex2(bf_lo(x1) * kLog2e - m0));
  p1 = pack2(ex2(bf_hi(x0) * kLog2e - m1), ex2(bf_hi(x1) * kLog2e - m1));
}

__device__ __forceinline__ void halo_read(uint32_t (&kpv)[10], uint32_t (&vpv)[10], uint32_t (&tg)[7], const uint4* hp) {
#pragma unroll
  for (int j = 0; j < 7; j++) {
    uint32_t x0, x1, x2;
    asm volatile("ld.relaxed.gpu.global.v4.u32 {%0, %1, %2, %3}, [%4];"
                 : "=r"(x0), "=r"(x1), "=r"(x2), "=r"(tg[j]) : "l"(hp + 32 * j) : "memory");
    if (j < 4) kpv[3 * j] = x0; else vpv[3 * j - 10] = x0;
    if (j < 3) kpv[3 * j + 1] = x1; else vpv[3 * j - 9] = x1;
    if (j < 3) kpv[3 * j + 2] = x2; else if (j < 6) vpv[3 * j - 8] = x2;
  }
}

template <int ROT>
__device__ __forceinline__ void pack_qkv(const float* acc, uint32_t (&qlo)[10], uint32_t (&qhi)[10], uint32_t (&klo)[10],
                                         uint32_t (&khi)[10], uint32_t (&vlo)[10], uint32_t (&vhi)[10]) {
#pragma unroll
  for (int j = 0; j < 10; j++) {
    const int x = (j + ROT) % 10, tq = x < 8 ? x : 16 + x, tk = x < 8 ? 8 + x : 18 + x, tv = x < 8 ? 16 + x : 20 + x;
    khi[j] = pack2(acc[4 * tk + 2], acc[4 * tk + 3]);
    vhi[j] = movm(pack2(acc[4 * tv + 2], acc[4 * tv + 3]));
    qlo[j] = pack2(acc[4 * tq], acc[4 * tq + 1]);
    qhi[j] = pack2(acc[4 * tq + 2], acc[4 * tq + 3]);
    klo[j] = pack2(acc[4 * tk], acc[4 * tk + 1]);
    vlo[j] = pack2(acc[4 * tv], acc[4 * tv + 1]);
    asm volatile("" : "+r"(khi[j]), "+r"(qlo[j]), "+r"(qhi[j]), "+r"(klo[j]), "+r"(vlo[j]));
  }
}

template <int ROT> __device__ __forceinline__ void halo_send(const float* acc, uint4* ho, uint32_t tag) {
#pragma unroll
  for (int j = 0; j < 7; j++) {
    uint32_t x[3];
#pragma unroll
    for (int e = 0; e < 3; e++) {
      const int i = 3 * j + e, y = (i % 10 + ROT) % 10, tk = y < 8 ? 8 + y : 18 + y, tv = y < 8 ? 16 + y : 20 + y;
      x[e] = i < 10 ? pack2(acc[4 * tk + 2], acc[4 * tk + 3]) : i < 20 ? movm(pack2(acc[4 * tv + 2], acc[4 * tv + 3])) : 0u;
    }
    asm volatile("st.relaxed.gpu.global.v4.u32 [%0], {%1, %2, %3, %4};" ::"l"(ho + 32 * j), "r"(x[0]), "r"(x[1]), "r"(x[2]), "r"(tag) : "memory");
  }
}

__device__ __forceinline__ void attention(float* acc, uint32_t sb, int b, int par, int w, int lane, uint32_t tag) {
  const int g = lane >> 2, t = lane & 3;
  uint32_t klo[10], khi[10], vlo[10], vhi[10], qlo[10], qhi[10], kpv[10], vpv[10];
  if (HALO_FIRST && w == 3 && b < NCTA - 8) {
    uint4* ho = g_halo + (b * 2 + par) * 224 + lane;
    if (tail_first(b & 7)) halo_send<8>(acc, ho, tag);
    else halo_send<0>(acc, ho, tag);
    TSIF(par == 0, 76);
    pin<120>(acc);
  }
  if (tail_first(b & 7)) pack_qkv<8>(acc, qlo, qhi, klo, khi, vlo, vhi);
  else pack_qkv<0>(acc, qlo, qhi, klo, khi, vlo, vhi);
  const uint32_t xa = sb + OFF_KVX + (par * 3) * 2560 + lane * 16;
  if (w < 3) {
    sts128(xa + w * 2560, khi[0], khi[1], khi[2], khi[3]);
    sts128(xa + w * 2560 + 512, khi[4], khi[5], khi[6], khi[7]);
    sts128(xa + w * 2560 + 1024, khi[8], khi[9], vhi[0], vhi[1]);
    sts128(xa + w * 2560 + 1536, vhi[2], vhi[3], vhi[4], vhi[5]);
    sts128(xa + w * 2560 + 2048, vhi[6], vhi[7], vhi[8], vhi[9]);
  } else if (!HALO_FIRST && b < NCTA - 8) {
    uint4* ho = g_halo + (b * 2 + par) * 224 + lane;
#pragma unroll
    for (int j = 0; j < 7; j++) {
      const uint32_t x0 = j < 4 ? khi[3 * j] : vhi[3 * j - 10], x1 = j < 3 ? khi[3 * j + 1] : vhi[3 * j - 9];
      const uint32_t x2 = j < 3 ? khi[3 * j + 2] : j < 6 ? vhi[3 * j - 8] : 0u;
      asm volatile("st.relaxed.gpu.global.v4.u32 [%0], {%1, %2, %3, %4};" ::"l"(ho + 32 * j), "r"(x0), "r"(x1), "r"(x2), "r"(tag) : "memory");
    }
  }
  TSIF(par == 0 && w == 1, 64);
  TSIF(par == 0 && w == 3 && !HALO_FIRST, 76);
#pragma unroll
  for (int j = 0; j < 10; j++) vlo[j] = movm(vlo[j]);
  const bool far0 = 2 * t > g, far1 = 2 * t + 1 > g;
  const uint32_t mfar = (far0 ? 0x0000FFFFu : 0u) | (far1 ? 0xFFFF0000u : 0u);
  float slo[4][2], shi[4][2], lg[2][2];
  uint32_t phi[4], plo[4], qml[4], qmh[4];
#pragma unroll
  for (int h = 0; h < 4; h++) {
    const int f = h == 0 ? 0 : h == 1 ? 3 : h == 2 ? 5 : 8, hf = h < 2 ? 2 : 7;
    const bool mine = (h & 1) ? t >= 2 : t < 2;
    qml[h] = mine ? qlo[hf] : 0u;
    qmh[h] = mine ? qhi[hf] : 0u;
    float a[4] = {0.f, 0.f, 0.f, 0.f}, c[4] = {0.f, 0.f, 0.f, 0.f};
    mma16816(a, qlo[f], qhi[f], qlo[f + 1], qhi[f + 1], klo[f], klo[f + 1]);
    mma16816(c, qlo[f], qhi[f], qlo[f + 1], qhi[f + 1], khi[f], khi[f + 1]);
    mma1688(a, qml[h], qmh[h], klo[hf]);
    mma1688(c, qml[h], qmh[h], khi[hf]);
    slo[h][0] = a[0];
    slo[h][1] = a[1];
    shi[h][0] = lg[h & 1][0] = far0 ? a[2] : c[2];
    shi[h][1] = lg[h & 1][1] = far1 ? a[3] : c[3];
    if (!ATT_MERGE && (h & 1)) softmax_two(lg, phi[h - 1], phi[h]);
  }
  TSIF(par == 0 && w == 1, 65);
  wg_sync(1 + par);
  TSIF(par == 0 && w == 1, 66);
  const bool nohist = (w == 0) && (b < 8);
  const uint4* hp = g_halo + ((b - 8) * 2 + par) * 224 + lane;
  uint32_t tg[7];
  if (w > 0) {
    const uint4 v0 = lds128(xa + (w - 1) * 2560), v1 = lds128(xa + (w - 1) * 2560 + 512), v2 = lds128(xa + (w - 1) * 2560 + 1024);
    const uint4 v3 = lds128(xa + (w - 1) * 2560 + 1536), v4 = lds128(xa + (w - 1) * 2560 + 2048);
    kpv[0] = v0.x; kpv[1] = v0.y; kpv[2] = v0.z; kpv[3] = v0.w; kpv[4] = v1.x; kpv[5] = v1.y; kpv[6] = v1.z; kpv[7] = v1.w;
    kpv[8] = v2.x; kpv[9] = v2.y; vpv[0] = v2.z; vpv[1] = v2.w; vpv[2] = v3.x; vpv[3] = v3.y; vpv[4] = v3.z; vpv[5] = v3.w;
    vpv[6] = v4.x; vpv[7] = v4.y; vpv[8] = v4.z; vpv[9] = v4.w;
  } else if (nohist) {
#pragma unroll
    for (int j = 0; j < 10; j++) kpv[j] = vpv[j] = 0u;
  } else {
    TSIF(par == 0, 77);
    halo_read(kpv, vpv, tg, hp);
  }
  if (w == 0 && !nohist) {
    int spins = 0;
    while (true) {
      bool ok = true;
#pragma unroll
      for (int j = 0; j < 7; j++) ok = ok && tg[j] == tag;
      if (__all_sync(0xffffffffu, ok) || ++spins > SPIN_LIMIT) break;
      halo_read(kpv, vpv, tg, hp);
    }
    TSIF(par == 0, 79);
  }
#pragma unroll
  for (int h = 0; h < 4; h++) {
    const int f = h == 0 ? 0 : h == 1 ? 3 : h == 2 ? 5 : 8, hf = h < 2 ? 2 : 7;
    float a[4] = {0.f, 0.f, 0.f, 0.f};
    mma16816(a, qlo[f], qhi[f], qlo[f + 1], qhi[f + 1], kpv[f], kpv[f + 1]);
    mma1688(a, qml[h], qmh[h], kpv[hf]);
    const float ninf = __int_as_float(0xff800000);
    lg[h & 1][0] = far0 ? (nohist ? ninf : a[0]) : slo[h][0];
    lg[h & 1][1] = far1 ? (nohist ? ninf : a[1]) : slo[h][1];
    if (h & 1) {
      softmax_two(lg, plo[h - 1], plo[h]);
      if (ATT_MERGE) {
        const float lh[2][2] = {{shi[h - 1][0], shi[h - 1][1]}, {shi[h][0], shi[h][1]}};
        softmax_two(lh, phi[h - 1], phi[h]);
      }
    }
  }
  TSIF(par == 0 && w <= 1, 67 + w);
  uint32_t ov[20];
#pragma unroll
  for (int hp = 0; hp < 2; hp++) {
    const int hf = hp ? 7 : 2;
    float sh[4] = {0.f, 0.f, 0.f, 0.f}, i0 = 0.f, i1 = 0.f;
#pragma unroll
    for (int e = 0; e < 2; e++) {
      const int h = 2 * hp + e, f = h == 0 ? 0 : h == 1 ? 3 : h == 2 ? 5 : 8;
      const uint32_t a0 = plo[h] & mfar, a2 = plo[h] & ~mfar, a3 = phi[h] & mfar, c1 = phi[h] & ~mfar;
      float sum[4] = {0.f, 0.f, 0.f, 0.f};
      mma1688(sum, plo[h], phi[h], 0x3F803F80u);
      const float r0 = rcp(sum[0]), r1 = rcp(sum[2]);
#pragma unroll
      for (int j = f; j < f + 2; j++) {
        float o[4] = {0.f, 0.f, 0.f, 0.f};
        mma16816(o, a0, 0u, a2, a3, vpv[j], vlo[j]);
        mma1688(o, 0u, c1, vhi[j]);
        ov[2 * j] = pack2(o[0] * r0, o[1] * r0);
        ov[2 * j + 1] = pack2(o[2] * r1, o[3] * r1);
      }
      const bool mine = e ? g >= 4 : g < 4;
      mma16816(sh, a0, 0u, a2, a3, mine ? vpv[hf] : 0u, mine ? vlo[hf] : 0u);
      mma1688(sh, 0u, c1, mine ? vhi[hf] : 0u);
      if (e == 0 || t >= 2) {
        i0 = r0;
        i1 = r1;
      }
    }
    ov[2 * hf] = pack2(sh[0] * i0, sh[1] * i0);
    ov[2 * hf + 1] = pack2(sh[2] * i1, sh[3] * i1);
  }
  TS(32 + 4 * par + w);
  mbar_wait(sb + OFF_BAR + 8 * B_P1, 0);
  const uint32_t oa = sb + OFF_OA + (lane >> 4) * 2048 + (32 * w + 2 * (lane & 15) + par) * 16;
#pragma unroll
  for (int j = 0; j < 5; j++) stsm4(oa + 4096 * j, ov + 4 * j);
  TSIF(par == 0 && w == 0, 120);
  fence_async_smem();
  TSIF(par == 0 && w == 0, 121);
  __syncwarp();
  if (lane == 0) mbar_arrive(sb + OFF_BAR + 8 * B_ATTN);
  TSM(w == 0 || w == 2, 122 + par + (w == 2 ? 3 : 0));
}

struct Maps {
  CUtensorMap x, wm, wt, k, v, y, wo, qm, qt, om, ot, u;
};

__device__ __forceinline__ void load_stage(uint32_t sb, int kb, int b, const Maps& m) {
  const uint32_t st = sb + (kb & 3) * STAGE_BYTES, bar = sb + OFF_BAR + 8 * (B_FULL1 + (kb & 3));
  const int r = b >> 3, hg = b & 7, slab = kb - KV_KB;
  const bool kv = slab >= 0 && slab < 5;
  const uint32_t kbar = sb + OFF_BAR + 8 * (B_KV + slab), dst = sb + OFF_KVS + slab * KVS_BYTES;
  mbar_expect_tx(bar, STAGE_BYTES);
  if (kv) mbar_expect_tx(kbar, KVS_BYTES);
  tma_3d(st, &m.x, 64 * kb, 64 * r, 0, bar);
  if (kv && KV_MIX) tma_3d(dst, &m.k, 0, 32 * (b >> 1) - 3, 2 * slab + (b & 1), kbar);
  tma_3d(st + ST_W, &m.wm, 80 * hg + (tail_first(hg) ? 16 : 0), 64 * kb, 0, bar);
  if (kv && KV_MIX) tma_3d(dst + KVS_V, &m.v, 0, 32 * (b >> 1), 2 * slab + (b & 1), kbar);
  tma_3d(st + ST_WT, &m.wt, 80 * hg + (tail_first(hg) ? 0 : 64), 64 * kb, 0, bar);
  if (kv && !KV_MIX) tma_3d(dst, &m.k, 0, 32 * (b >> 1) - 3, 2 * slab + (b & 1), kbar);
  if (kv && !KV_MIX) tma_3d(dst + KVS_V, &m.v, 0, 32 * (b >> 1), 2 * slab + (b & 1), kbar);
}

__global__ void __launch_bounds__(NTHR, 1) fused_kernel(const __grid_constant__ Maps m, const Params p) {
  extern __shared__ __align__(1024) uint8_t smem[];
  const uint32_t sb = (uint32_t)__cvta_generic_to_shared(smem);
  const uint32_t bars = sb + OFF_BAR;
  const int tid = threadIdx.x, lane = tid & 31;
  int b = blockIdx.x;
  if (BMAP == 1) b = (((b & 63) >> 3) * 2 + (b & 1)) * 8 + (((b < 64 ? 0x6521 : 0x7430) >> (4 * ((b >> 1) & 3))) & 7);
  if (BMAP == 2) b = ((b & 63) >> 2) * 8 + (((b < 64 ? 0x6521 : 0x7430) >> (4 * (b & 3))) & 7);
  if (BMAP == 3) b = (((b & 63) >> 3) * 2 + (b & 1)) * 8 + (((b < 64 ? 0x7430 : 0x6521) >> (4 * ((b >> 1) & 3))) & 7);
  if (BMAP == 4) b = (((b >> 4) * 2 + (b & 1)) * 8) + ((b >> 1) & 7);
  if (BMAP == 5) b = 127 - b;
  const int r = b >> 3, hg = b & 7;

  if (tid == T_ISSUE) {
    TSM(true, 0);
#pragma unroll
    for (int i = 0; i < 4; i++) mbar_init(bars + 8 * (B_FULL1 + i), 1);
#pragma unroll
    for (int i = 0; i < 3; i++) mbar_init(bars + 8 * (B_KV + i), 1);
    fence_async_smem();
    TS(84);
#pragma unroll 1
    for (int kb = 0; kb <= PRE2; kb++) {
      load_stage(sb, kb, b, m);
      TS(85 + kb);
    }
  } else if (tid >= T_PF && tid < T_PF + 12) {
    tm_prefetch(&m.x + (tid - T_PF));
  } else if (tid == T_INIT) {
#pragma unroll
    for (int i = 0; i < 4; i++) mbar_init(bars + 8 * (B_EMPTY1 + i), 8);
#pragma unroll
    for (int i = 0; i < 8; i++) mbar_init(bars + 8 * (B_FULL2 + i), 1);
#pragma unroll
    for (int i = 0; i < 4; i++) mbar_init(bars + 8 * (B_EMPTY2 + i), 8);
#pragma unroll
    for (int i = 0; i < 4; i++) mbar_init(bars + 8 * (B_U + i), 1);
    mbar_init(bars + 8 * B_HA, 4);
    mbar_init(bars + 8 * B_GATE, 4);
    mbar_init(bars + 8 * B_HB, 1);
    mbar_init(bars + 8 * B_KVD, 4);
    mbar_init(bars + 8 * B_QF, 1);
    mbar_init(bars + 8 * B_ATTN, 8);
    mbar_init(bars + 8 * B_P1, 8);
    mbar_init(bars + 8 * B_C34, 1);
#pragma unroll
    for (int i = 0; i < 5; i++) mbar_init(bars + 8 * (B_YST + i), 4);
#pragma unroll
    for (int i = 0; i < 5; i++) mbar_init(bars + 8 * (B_US + i), 4);
    mbar_init(bars + 8 * B_YSIG, 1);
    mbar_init(bars + 8 * B_YFULL, 1);
    mbar_init(bars + 8 * B_EPOCH, 1);
    mbar_init(bars + 8 * B_PREP, 4);
    mbar_init(bars + 8 * B_USIG, 1);
    mbar_init(bars + 8 * B_WST, 1);
#pragma unroll
    for (int i = 3; i < 5; i++) mbar_init(bars + 8 * (B_KV + i), 1);
    mbar_init(bars + 8 * B_E3, 8);
    mbar_init(bars + 8 * B_LAST, 1);
    mbar_init(bars + 8 * B_OSIG, 1);
    mbar_init(bars + 8 * B_WOP, 1);
    fence_async_smem();
  }
  const int warp = __shfl_sync(0xffffffffu, tid >> 5, 0), wg = warp >> 2, w = warp & 3;
  __syncthreads();
  TSIF(tid == 0, 87);

  if (wg == 3) {
    asm volatile("setmaxnreg.dec.sync.aligned.u32 56;");
    if (w == 0) {
      if (lane == 0) {
#pragma unroll 1
        for (int kb = 1 + PRE2; kb < 10; kb++) {
          if (kb >= 4) mbar_wait(bars + 8 * (kb == 7 ? B_E3 : B_EMPTY1 + (kb & 3)), (kb >> 3) & 1);
          TSIF(kb >= 4, 44 + kb);
          load_stage(sb, kb, b, m);
          TSIF(kb == 3, 60);
          if (kb == TRIG_KB) mbar_arrive(bars + 8 * B_LAST);
        }
        mbar_wait(bars + 8 * B_WOP, 0);
        mbar_wait(bars + 8 * WL_TRIG, 0);
        mbar_wait(bars + 8 * B_EPOCH, 0);
        flag_wait(g_cnt + C_W + 32 * hg, (lds32(sb + OFF_EPOCH) + 1) * 16);
        TS(30);
#pragma unroll 1
        for (int j = 0; j < 8; j++) {
          if (j >= 6) mbar_wait(bars + 8 * (B_EMPTY2 + j - 6), 0);
          if (j == 4) mbar_wait(bars + 8 * B_ATTN, 0);
          TSIF(j >= 6, 100 + j);
          if (RF_GATE && j == 6) mbar_wait(bars + 8 * B_YSIG, 0);
          mbar_expect_tx(bars + 8 * (B_FULL2 + j), j == 0 ? WO_BYTES : j == 5 ? O_BYTES + WO_BYTES + 512 : O_BYTES + WO_BYTES);
          bulk_load(sb + off_w(j), g_WO + (hg * 8 + step_src(hg, j)) * 800, WO_BYTES, bars + 8 * (B_FULL2 + j));
        }
        mbar_wait(bars + 8 * (B_EMPTY2 + 3), 0);
        mbar_expect_tx(bars + 8 * B_QF, O_BYTES);
        tma_2d(sb + OFF_QS, &m.qm, 80 * hg, 128 * r, bars + 8 * B_QF);
        tma_2d(sb + OFF_QT, &m.qt, 80 * hg + 64, 128 * r, bars + 8 * B_QF);
      }
    } else if (w == 1) {
      unsigned epoch = 0;
      if (lane == 0) {
        epoch = atomicAdd(g_cnt + C_LAUNCH, 1u) / NCTA;
        asm volatile("st.shared.u32 [%0], %1;" ::"r"(sb + OFF_EPOCH), "r"(epoch) : "memory");
        mbar_arrive(bars + 8 * B_EPOCH);
        mbar_wait(bars + 8 * B_KVD, 0);
        mbar_expect_tx(bars + 8 * B_HB, 5 * 4096);
#pragma unroll 1
        for (int c = 0; c < 5; c++) {
          if (c == 3) mbar_wait(bars + 8 * B_S3, 0);
          bulk_load(sb + off_ch(c) + U_BYTES, p.ssm_k + (5 * b + c) * SEQ, 4096, bars + 8 * B_HB);
        }
#pragma unroll
        for (int c = 0; c < 4; c++) mbar_expect_tx(bars + 8 * (B_U + c), c < 3 ? U_BYTES : 2 * U_BYTES);
        const uint4* usrc = g_U + 5 * b * U_PITCH;
        mbar_wait(bars + 8 * B_USIG, 0);
        flag_wait(g_cnt + C_PREP + 32 * (b & 15), (epoch + 1) * NCTA);
        TS(23);
#pragma unroll
        for (int c = 0; c < 5; c++) {
          if (c == 3) mbar_wait(bars + 8 * (B_U + 2), 0);
          bulk_load(sb + off_ch(c), usrc + c * U_PITCH, U_BYTES, bars + 8 * (B_U + (c < 3 ? c : 3)));
          TSIF(c == 0 || c == 4, 116 + (c >> 2));
        }
      }
      epoch = __shfl_sync(0xffffffffu, epoch, 0);
      if (lane < 8) {
        const int src = (b & ~7) | step_src(hg, lane);
        mbar_wait(bars + 8 * B_OSIG, 0);
        TS(20);
        flag_wait(g_cnt + C_O + 32 * src, epoch + 1);
        if (lane >= 1 && lane < 4) bulk_load(sb + off_o(lane), g_O + src * 1280, O_BYTES, bars + 8 * (B_FULL2 + lane));
        __syncwarp(0xff);
        TS(21);
        if (lane == 5) bulk_load(sb + OFF_GATE, g_gate + 128 * r, 512, bars + 8 * (B_FULL2 + 5));
#pragma unroll 1
        for (int j = 4; j < 8; j++) {
          if (lane == j) {
            mbar_wait(bars + 8 * (j < 6 ? B_C34 : B_EMPTY2 + j - 6), 0);
            if (RF_GATE && j == 6) mbar_wait(bars + 8 * B_YSIG, 0);
            bulk_load(sb + off_o(j), g_O + src * 1280, O_BYTES, bars + 8 * (B_FULL2 + j));
          }
          __syncwarp(0xff);
        }
        TS(22);
      }
    } else if (w == 2) {
      mbar_wait(bars + 8 * B_PREP, 0);
      flag_signal(g_cnt + C_PREP, 16, lane);
      TS(25);
      if (lane == 0) mbar_arrive(bars + 8 * B_USIG);
      mbar_wait(bars + 8 * B_GATE, 0);
      if ((NOMB & 1) && lane == 0) asm volatile("fence.release.gpu;" ::: "memory");
      mbar_wait(bars + 8 * B_ATTN, 0);
      if (lane == 0) {
        if (O_DEFER) mbar_wait(bars + 8 * (B_U + 3), 0);
        asm volatile("cp.async.bulk.global.shared::cta.bulk_group [%0], [%1], 20480;\ncp.async.bulk.commit_group;\n"
                     "cp.async.bulk.wait_group 0;\nfence.proxy.async.global;" ::"l"(g_O + b * 1280), "r"(sb + OFF_OA) : "memory");
      }
      TS(74);
      if (!(NOMB & 1)) flag_signal(g_cnt + C_O + 32 * b, 1, lane);
      else if (lane == 0) flag_bump(g_cnt + C_O + 32 * b);
      TS(26);
      if (lane == 0) mbar_arrive(bars + 8 * B_OSIG);

    } else {
      if (lane == 0) {
        uint4* dst = g_WO + (hg * 8 + (r >> 1)) * 800 + (r & 1) * 80;
        mbar_wait(bars + 8 * B_P1, 0);
        mbar_wait(bars + 8 * WB_TRIG, 0);
        mbar_expect_tx(bars + 8 * B_WST, WO_BYTES / 2);
        tma_3d(sb + OFF_WS, &m.wo, 0, 40 * r, 5 * hg, bars + 8 * B_WST);
        mbar_wait(bars + 8 * B_WST, 0);
        mbar_wait(bars + 8 * WO_TRIG, 0);
#pragma unroll 1
        for (int n = 0; n < 5; n++)
          asm volatile("cp.async.bulk.global.shared::cta.bulk_group [%0], [%1], 1280;" ::"l"(dst + 160 * n), "r"(sb + OFF_WS + 1280 * n) : "memory");
        asm volatile("cp.async.bulk.commit_group;\ncp.async.bulk.wait_group 0;\nfence.proxy.async.global;" ::: "memory");
        if (!(NOMB & 4)) asm volatile("fence.release.gpu;" ::: "memory");
        flag_bump(g_cnt + C_W + 32 * hg);
        mbar_arrive(bars + 8 * B_WOP);
        TS(71);
#pragma unroll 1
        for (int c = 0; c < 5; c++) {
          mbar_wait(bars + 8 * (B_YST + c), 0);
          asm volatile("cp.async.bulk.global.shared::cta.bulk_group [%0], [%1], 4096;\ncp.async.bulk.commit_group;"
                       ::"l"(g_Y + (5 * b + c) * Y_PITCH), "r"(sb + off_ch(c)) : "memory");
          if (c == 2) {
            asm volatile("cp.async.bulk.wait_group.read 0;" ::: "memory");
            mbar_arrive(bars + 8 * B_C34);
          }
        }
        asm volatile("cp.async.bulk.wait_group 0;\nfence.proxy.async.global;" ::: "memory");
        TS(75);
        if (!(NOMB & 2)) asm volatile("fence.release.gpu;" ::: "memory");
        flag_bump(g_cnt + C_Y + 32 * (b >> 4));
        TS(27);
        mbar_arrive(bars + 8 * B_YSIG);
        mbar_expect_tx(bars + 8 * B_YFULL, 20480);
        flag_wait(g_cnt + C_Y + 32 * hg, (lds32(sb + OFF_EPOCH) + 1) * 16);
        TS(24);
        tma_2d(sb + OFF_YT, &m.y, 128 * r, 80 * hg, bars + 8 * B_YFULL);
        tma_2d(sb + OFF_YT + 10240, &m.y, 128 * r + 64, 80 * hg, bars + 8 * B_YFULL);
      }
    }
  } else {
    asm volatile("setmaxnreg.inc.sync.aligned.u32 152;");
    if (wg < 2) {
      float acc[120];
#pragma unroll
      for (int i = 0; i < 120; i++) acc[i] = 0.f;
      const uint32_t da = desc_lo(sb + wg * 8192, 16), db = desc_lo(sb + ST_W, 8192), dc = desc_lo(sb + ST_WT, 2048);
      if (PW1) pin<120>(acc);
      if (PW1 == 2) mbar_wait(bars + 8 * B_FULL1, 0);
#pragma unroll 1
      for (int kb = 0; kb < 10; kb++) {
        mbar_wait(bars + 8 * (B_FULL1 + (kb & 3)), (kb >> 2) & 1);
        const uint32_t so = (kb & 3) * (STAGE_BYTES >> 4);
        wg_fence();
#pragma unroll
        for (int k = 0; k < 4; k++) {
          WgSST<192>::mma<HI_SW128, HI_SW128>(acc, da + so + 2 * k, db + so + 128 * k, 1);
          WgSST<48>::mma<HI_SW128, HI_SW32>(acc + 96, da + so + 2 * k, dc + so + 32 * k, 1);
        }
        wg_commit();
        wg_wait<1>();
        if (kb > 0 && lane == 0) mbar_arrive(bars + 8 * (kb == 4 ? B_E3 : B_EMPTY1 + ((kb - 1) & 3)));
      }
      mbar_wait(bars + 8 * B_EPOCH, 0);
      const uint32_t tag = lds32(sb + OFF_EPOCH) + 1;
      mbar_wait(bars + 8 * B_S3, 0);
      wg_wait<0>();
      pin<120>(acc);
      if (lane == 0) mbar_arrive(bars + 8 * B_P1);
      TSM(w == 0, 3 + wg);
      attention(acc, sb, b, wg, w, lane, tag);
    } else {
      const int tw = tid & 127, chl = 64 * (b & 1) + 8 * w + (lane >> 2);
      uint4* up = g_U + chl * U_PITCH + ((4 * (b >> 1) + (lane & 3)) ^ ((b >> 2) & 1));
      uint2 sw[10];
      uint32_t dv = 0;
      if (lane < 5) dv = __ldg(reinterpret_cast<const unsigned short*>(p.ssm_D) + 5 * b + lane);
#pragma unroll
      for (int i = 0; i < 10; i++) sw[i] = ldg64(reinterpret_cast<const uint2*>(p.shift_k) + chl + 128 * (i >> 1) + 32 * (i & 1));
      uint32_t tab[12];
      float tt[4];
      fft_tables(tab, tw);
      fft_twiddles(tt, tw);
      uint4 res[10];
#pragma unroll
      for (int i = 0; i < 10; i++) res[i] = make_uint4(0, 0, 0, 0);
#pragma unroll 1
      for (int slab = 0; slab < 5; slab++) {
#pragma unroll
        for (int i = 0; i < 8; i++) res[i] = res[i + 2];
        prep_slab(res + 8, sw, sb, slab, w, lane);
        TSIF(w == 0, 99 + 4 * slab);
#pragma unroll
        for (int i = 0; i < 8; i++) sw[i] = sw[i + 2];
      }
      TSIF(w == 0, 28);
      __syncwarp();
      if (lane == 0) mbar_arrive(bars + 8 * B_KVD + ((res[8].x ^ res[9].x) & p.zero));
      mbar_wait(bars + 8 * B_KVD, 0);
      fft_tables_store(tab, sb, tw);
      mbar_wait(bars + 8 * B_LAST, 0);
#pragma unroll
      for (int i = 0; i < 10; i++) up[(128 * (i >> 1) + 32 * (i & 1)) * U_PITCH] = res[i];
      __syncwarp();
      if (lane == 0) mbar_arrive(bars + 8 * B_PREP);
      TSIF(w == 0 && !U_TMA, 5);
      mbar_wait(bars + 8 * (G_AFTER ? B_USIG : B_LAST), 0);
      prep_gate(p, b, w, lane);
      __syncwarp();
      if (lane == 0) mbar_arrive(bars + 8 * B_GATE);
      TSIF(w == 0, 72);
      mbar_wait(bars + 8 * B_HB, 0);
      TSIF(w == 0, 2);
      const uint32_t ha = sb + U_BYTES + ((tw >> 3) * 16 + 8 + (tw & 7)) * 16;
      uint4 hv[5];
#pragma unroll
      for (int c = 0; c < 5; c++) hv[c] = lds128(ha + off_ch(c));
      __syncwarp();
#pragma unroll
      for (int c = 0; c < 5; c++) sts128((ha ^ 16) + off_ch(c), hv[c].x, hv[c].y, hv[c].z, hv[c].w);
      sts128(sb + OFF_TT + 16 * tw, __float_as_uint(tt[0]), __float_as_uint(tt[1]), __float_as_uint(tt[2]), __float_as_uint(tt[3]));
      if (tw < 5) asm volatile("st.shared.f32 [%0], %1;" ::"r"(sb + OFF_D + 4 * tw), "f"(bf_lo(dv) * 0.125f) : "memory");
      fence_async_smem();
      __syncwarp();
      if (lane == 0) mbar_arrive(bars + 8 * B_HA);
      TSIF(w == 0, 6);
    }

    FftConst fc;
    TSM(w == 0 && wg == 0, 104);
    mbar_wait(bars + 8 * B_HA, 0);
    fft_matrices(fc, sb, w, lane);
    TSM(w == 0 && wg == 0, 105);
    if (ATT_GATE && !H_EARLY) mbar_wait(bars + 8 * B_ATTN, 0);
    TSM(w == 0 && wg == 2, 124);
#pragma unroll 1
    for (uint32_t tasks = wg == 0 ? TASK0 : wg == 1 ? TASK1 : TASK2; tasks; tasks >>= 4) {
      const int c = (tasks & 7) - 1;
      conv_channel(fc, sb, c, wg, w, lane);
      if (lane == 0) mbar_arrive(bars + 8 * (B_YST + c));
      TSM(w == 0, 10 + c);
    }

    if (wg < 2) {
      const int g = lane >> 2;
      float acc[40];
#pragma unroll
      for (int i = 0; i < 40; i++) acc[i] = 0.f;
      const uint32_t da = desc_lo(sb + wg * 1024, 2048), db = desc_lo(sb, 2560);
      mbar_wait(bars + 8 * B_ATTN, 0);
      mbar_wait(bars + 8 * (B_YST + 3), 0);
      mbar_wait(bars + 8 * (B_YST + 4), 0);
      if (PW2) mbar_wait(bars + 8 * B_FULL2, 0);
      TSM(w == 0, 15 + wg);
#pragma unroll 1
      for (int j = 0; j < 8; j++) {
        mbar_wait(bars + 8 * (B_FULL2 + j), 0);
        const uint32_t oa = da + (off_o(j) >> 4), ob = db + (off_w(j) >> 4);
        wg_fence();
#pragma unroll
        for (int k = 0; k < 5; k++) WgSST<80>::mma<HI_NONE, HI_SW32>(acc, oa + 256 * k, ob + 32 * k, 1);
        wg_commit();
        wg_wait<1>();
        if (j >= 1 && j <= 4 && lane == 0) mbar_arrive(bars + 8 * (B_EMPTY2 + j - 1));
      }
      TSIF(w == 0 && wg == 0, 113);
      const int tr = 64 * wg + 16 * w + (lane & 15);
      const uint32_t fm = sb + OFF_QS + tr * 128, fx = (lane >> 4) ^ (tr & 7);
      const uint32_t ft = sb + OFF_QT + tr * 32 + (((lane >> 4) ^ (tr >> 2)) & 1) * 16;
      const float g0 = __uint_as_float(lds32(sb + OFF_GATE + (64 * wg + 16 * w + g) * 4));
      const float g1 = __uint_as_float(lds32(sb + OFF_GATE + (64 * wg + 16 * w + 8 + g) * 4));
      const uint32_t ga = pack2(g0, g0), gb = pack2(g1, g1);
      const uint32_t na = pack2(1.f - g0, 1.f - g0), nb = pack2(1.f - g1, 1.f - g1);

      wg_wait<0>();
      pin<40>(acc);
      TSM(w == 0, 17 + wg);
      uint32_t pb[20];
#pragma unroll
      for (int j = 0; j < 10; j++) {
        pb[2 * j] = bmul(na, pack2(acc[4 * j], acc[4 * j + 1]));
        pb[2 * j + 1] = bmul(nb, pack2(acc[4 * j + 2], acc[4 * j + 3]));
        asm volatile("" : "+r"(pb[2 * j]), "+r"(pb[2 * j + 1]));
      }
      const uint32_t ya = sb + OFF_YT + wg * 10240 + ((lane >> 4) * 8 + (lane & 7)) * 128 +
                          (((2 * w + (((lane >> 3) & 1) ^ wg)) ^ (lane & 7)) << 4);
      uint32_t qf[20];
      mbar_wait(bars + 8 * B_QF, 0);
#pragma unroll
      for (int j = 0; j < 5; j++) ldsm4(qf + 4 * j, j < 4 ? fm + ((fx ^ (2 * j)) << 4) : ft);
      mbar_wait(bars + 8 * B_YFULL, 0);
      TSM(w == 0 && wg == 0, 19);
#pragma unroll
      for (int j = 0; j < 5; j++) {
        uint32_t y[4];
        ldsm4t(y, ya + 2048 * j);
#pragma unroll
        for (int i = 0; i < 4; i++) qf[4 * j + i] = badd(bmul((i & 1) ? gb : ga, bmul(qf[4 * j + i], y[i])), pb[4 * j + i]);
      }
#pragma unroll
      for (int j = 0; j < 5; j++) stsm4(j < 4 ? fm + ((fx ^ (2 * j)) << 4) : ft, qf + 4 * j);
      fence_async_smem();
      __syncwarp();
      if (lane == 0) {
        const int row = 64 * wg + 16 * w;
        asm volatile("cp.async.bulk.tensor.2d.global.shared::cta.bulk_group [%0, {%2, %3}], [%1];"
                     ::"l"(&m.om), "r"(sb + OFF_QS + row * 128), "r"(80 * hg), "r"(128 * r + row) : "memory");
        asm volatile("cp.async.bulk.tensor.2d.global.shared::cta.bulk_group [%0, {%2, %3}], [%1];"
                     ::"l"(&m.ot), "r"(sb + OFF_QT + row * 32), "r"(80 * hg + 64), "r"(128 * r + row) : "memory");
        asm volatile("cp.async.bulk.commit_group;\ncp.async.bulk.wait_group.read 0;" ::: "memory");
      }
      TSM(true, 40 + 4 * wg + w);
      if (ENDBAR) asm volatile("bar.sync 15, 256;" ::: "memory");
    }
  }
}

typedef CUresult (*EncodeFn)(CUtensorMap*, CUtensorMapDataType, cuuint32_t, void*, const cuuint64_t*, const cuuint64_t*,
                             const cuuint32_t*, const cuuint32_t*, CUtensorMapInterleave, CUtensorMapSwizzle,
                             CUtensorMapL2promotion, CUtensorMapFloatOOBfill);

void encode(EncodeFn fn, CUtensorMap* tm, const void* base, int rank, const cuuint64_t* dims, const cuuint64_t* strides,
            const cuuint32_t* box, CUtensorMapSwizzle swz) {
  const cuuint32_t ones[3] = {1, 1, 1};
  fn(tm, CU_TENSOR_MAP_DATA_TYPE_BFLOAT16, rank, const_cast<void*>(base), dims, strides, box, ones,
     CU_TENSOR_MAP_INTERLEAVE_NONE, swz, CU_TENSOR_MAP_L2_PROMOTION_L2_128B, CU_TENSOR_MAP_FLOAT_OOB_FILL_NONE);
}

}

extern "C" void kernel_launch(void* const* d_in, const int* in_sizes, int n_in, void* d_out, int out_size) {
  (void)in_sizes; (void)n_in; (void)out_size;
  Params p;
  p.q = (const __nv_bfloat16*)d_in[0];
  p.k = (const __nv_bfloat16*)d_in[1];
  p.v = (const __nv_bfloat16*)d_in[2];
  p.shift_k = (const __nv_bfloat16*)d_in[3];
  p.ssm_k = (const __nv_bfloat16*)d_in[4];
  p.ssm_D = (const __nv_bfloat16*)d_in[5];
  p.wqkv = (const __nv_bfloat16*)d_in[7];
  p.wo = (const __nv_bfloat16*)d_in[8];
  p.gate_w = (const __nv_bfloat16*)d_in[9];
  p.out = (__nv_bfloat16*)d_out;
  p.zero = 0;

  static EncodeFn fn = nullptr;
  static void *yaddr = nullptr, *uaddr = nullptr;
  if (!fn) {
    cudaDriverEntryPointQueryResult qr;
    void* f = nullptr;
    cudaGetDriverEntryPoint("cuTensorMapEncodeTiled", &f, cudaEnableDefault, &qr);
    fn = (EncodeFn)f;
    cudaGetSymbolAddress(&yaddr, g_Y);
    cudaGetSymbolAddress(&uaddr, g_U);
    cudaFuncSetAttribute(fused_kernel, cudaFuncAttributeMaxDynamicSharedMemorySize, SMEM_BYTES);
  }
  Maps m;
  {
    const cuuint64_t dims[3] = {640, 1024, 2}, st[2] = {2560, 1280};
    const cuuint32_t box[3] = {64, 64, 2};
    encode(fn, &m.x, p.q, 3, dims, st, box, CU_TENSOR_MAP_SWIZZLE_128B);
  }
  {
    const cuuint64_t dims[3] = {640, 640, 3}, st[2] = {3840, 1280};
    const cuuint32_t box[3] = {64, 64, 3}, boxt[3] = {16, 64, 3};
    encode(fn, &m.wm, p.wqkv, 3, dims, st, box, CU_TENSOR_MAP_SWIZZLE_128B);
    encode(fn, &m.wt, p.wqkv, 3, dims, st, boxt, CU_TENSOR_MAP_SWIZZLE_32B);
  }
  {
    const cuuint64_t dims[3] = {64, 2048, 10}, st[2] = {1280, 128};
    const cuuint32_t boxk[3] = {64, 35, 1}, boxv[3] = {64, 32, 1};
    encode(fn, &m.k, p.k, 3, dims, st, boxk, CU_TENSOR_MAP_SWIZZLE_128B);
    encode(fn, &m.v, p.v, 3, dims, st, boxv, CU_TENSOR_MAP_SWIZZLE_128B);
  }
  {
    const cuuint64_t dims[3] = {16, 640, 40}, st[2] = {1280, 32};
    const cuuint32_t box[3] = {16, 40, 5};
    encode(fn, &m.wo, p.wo, 3, dims, st, box, CU_TENSOR_MAP_SWIZZLE_32B);
  }
  {
    const cuuint64_t dims[2] = {2048, 640}, st[1] = {Y_PITCH * 16};
    const cuuint32_t box[2] = {64, 80};
    encode(fn, &m.y, yaddr, 2, dims, st, box, CU_TENSOR_MAP_SWIZZLE_128B);
    const cuuint64_t stu[1] = {U_PITCH * 16};
    const cuuint32_t boxu[2] = {32, 64};
    encode(fn, &m.u, uaddr, 2, dims, stu, boxu, CU_TENSOR_MAP_SWIZZLE_NONE);
  }
  {
    const cuuint64_t dims[2] = {640, 2048}, st[1] = {1280};
    const cuuint32_t bqm[2] = {64, 128}, bqt[2] = {16, 128}, bom[2] = {64, 16}, bot[2] = {16, 16};
    encode(fn, &m.qm, p.q, 2, dims, st, bqm, CU_TENSOR_MAP_SWIZZLE_128B);
    encode(fn, &m.qt, p.q, 2, dims, st, bqt, CU_TENSOR_MAP_SWIZZLE_32B);
    encode(fn, &m.om, p.out, 2, dims, st, bom, CU_TENSOR_MAP_SWIZZLE_128B);
    encode(fn, &m.ot, p.out, 2, dims, st, bot, CU_TENSOR_MAP_SWIZZLE_32B);
  }
  fused_kernel<<<NCTA, NTHR, SMEM_BYTES>>>(m, p);
}
```

```cpp
#include <cuda.h>
#include <cuda_bf16.h>
#include <cuda_runtime.h>
#include <stdint.h>

namespace {

constexpr int SEQ = 2048, DIM = 640, NCTA = 128, NTHR = 512;

#define TRIG_KB 9
#define KV_KB 2
#define DEV_EXIT 0
#define ATT_GATE 1
#define G_AFTER 0
#define FENCE_LO 0
#define FENCE_HI 0
#define PW1 2
#define PW2 1
#define ENDBAR 0
#define PAD_KB 0
#define Y_ALIAS 1
#define H_EARLY 1
#define NOMB 0
#define SRC_ROT 0
#define WAIT_NS 0
#define WB_TRIG B_USIG
#define G_POS 0
#define TAILF 1
#define T_ISSUE 384
#define T_PF 416
#define T_INIT 448
#define ATT_MERGE 0
#define BMAP 1
#define PRE2 1
#define KV_MIX 0
#define O_DEFER 0
#define TASK0 0x52
#define TASK1 0x3
#define TASK2 0x41
#define HALO_FIRST 1
#define PREV_EARLY 0
#define CP0 1
#define ACQ 0
#define U_TMA 0
#define U_GATE 0
#define RF_GATE 0
#define WO_TRIG B_WST
#define WL_TRIG B_WOP
#define WO_GATE 1

constexpr uint32_t STAGE_BYTES = 47104, ST_W = 16384, ST_WT = 40960;
constexpr uint32_t O_BYTES = 20480, WO_BYTES = 12800;
constexpr uint32_t OFF_OA = 0;
constexpr uint32_t OFF_QS = 3 * O_BYTES, OFF_QT = OFF_QS + 16384;
constexpr uint32_t OFF_WC = 81920;
constexpr uint32_t OFF_WA = 94720;
constexpr uint32_t OFF_GATE = 145920;
constexpr uint32_t OFF_TT = 146432;
constexpr uint32_t OFF_KVX = 148480;
constexpr uint32_t OFF_CH3 = 163840;
constexpr uint32_t CH_BYTES = 12288, U_BYTES = 4096;
constexpr uint32_t OFF_FT = 225280, OFF_GT = 229376;
constexpr uint32_t OFF_CH0 = 188416;
constexpr uint32_t OFF_KVS = OFF_CH0, KVS_V = 4480, KVS_BYTES = 8576;
constexpr uint32_t OFF_WS = OFF_WA;
__device__ __forceinline__ uint32_t off_us(int s) { return OFF_CH0 + 4096 * ((0x65320 >> (4 * s)) & 7); }
constexpr uint32_t OFF_YT = 163840;
constexpr uint32_t OFF_BAR = 231936;
constexpr uint32_t SMEM_BYTES = OFF_BAR + 512;

enum : uint32_t {
  B_FULL1 = 0, B_EMPTY1 = 4, B_S3 = 7, B_FULL2 = 52, B_EMPTY2 = 13, B_U = 8, B_GATE = 12, B_HA = 19, B_HB = 20,
  B_ATTN = 21, B_C34 = 22, B_CONV = 23, B_YFULL = 24, B_EPOCH = 25, B_PREP = 26, B_P1 = 27, B_LAST = 28,
  B_E3 = 29, B_OSIG = 30, B_WOP = 31, B_USIG = 32, B_WST = 33, B_KV = 34, B_KVD = 39, B_QF = 17, B_YST = 40,
  B_US = 45, B_YSIG = 50
};
constexpr uint32_t OFF_EPOCH = OFF_BAR + 8 * 51, OFF_D = OFF_BAR + 8 * 60;
__device__ __forceinline__ uint32_t off_o(int j) { return j < 4 ? OFF_OA + j * O_BYTES : j < 6 ? OFF_CH0 + (j - 4) * O_BYTES : OFF_OA + (j - 6) * O_BYTES; }
__device__ __forceinline__ uint32_t off_w(int j) { return j < 4 ? OFF_WA + j * WO_BYTES : j == 4 ? OFF_KVX : j == 5 ? OFF_WC : OFF_WA + (j - 6) * WO_BYTES; }
__device__ __forceinline__ int step_src(int hg, int j) { return SRC_ROT ? (hg + j) & 7 : j == 0 ? hg : j <= hg ? j - 1 : j; }
__device__ __forceinline__ bool tail_first(int hg) { return TAILF && (hg & 3) == 3; }
__device__ __forceinline__ uint32_t off_ch(int c) { return (c < 3 ? OFF_CH0 : OFF_CH3 - 3 * CH_BYTES) + c * CH_BYTES; }

#define U_PITCH 264
__device__ __align__(1024) uint4 g_U[DIM * U_PITCH];
__device__ uint4 g_O[NCTA * 1280];
#define g_Y g_U
constexpr int Y_PITCH = U_PITCH;
__device__ uint4 g_WO[64 * 800];
__device__ uint4 g_halo[NCTA * 2 * 7 * 32];
__device__ float g_gate[SEQ + PAD_KB * 256];
__device__ unsigned g_cnt[32 * (1 + 2 * 16 + 8 + NCTA)];
constexpr int C_LAUNCH = 0, C_PREP = 32, C_Y = 32 * 17, C_W = 32 * 33, C_O = 32 * 41;

#define TSM(cond, slot) do { } while (0)
#define TSIF(cond, slot) do { if (__LINE__ >= FENCE_LO && __LINE__ < FENCE_HI) sched_fence(); } while (0)
__device__ __forceinline__ void sched_fence() {
  asm volatile("{\n.reg .pred p;\n.reg .u32 c;\nmov.u32 c, %%clock;\nsetp.eq.u32 p, c, 0;\n@p st.shared.u32 [%0], c;\n}"
               ::"r"(1024 + OFF_EPOCH + 4) : "memory");
}
#define TS(slot) TSIF(true, slot)

struct Params {
  const __nv_bfloat16 *q, *k, *v, *shift_k, *ssm_k, *ssm_D, *wqkv, *wo, *gate_w;
  __nv_bfloat16* out;
  uint32_t zero;
};

#define POLL_NS 0
constexpr int SPIN_LIMIT = 1 << 17;

__device__ __forceinline__ void mbar_init(uint32_t bar, uint32_t count) {
  asm volatile("mbarrier.init.shared::cta.b64 [%0], %1;" ::"r"(bar), "r"(count) : "memory");
}
__device__ __forceinline__ void mbar_expect_tx(uint32_t bar, uint32_t bytes) {
  asm volatile("mbarrier.arrive.expect_tx.shared::cta.b64 _, [%0], %1;" ::"r"(bar), "r"(bytes) : "memory");
}
__device__ __forceinline__ void mbar_arrive(uint32_t bar) {
  asm volatile("mbarrier.arrive.shared::cta.b64 _, [%0];" ::"r"(bar) : "memory");
}
__device__ __forceinline__ void mbar_wait(uint32_t bar, uint32_t parity) {
  uint32_t ok;
  int spins = 0;
  do {
    if (WAIT_NS)
      asm volatile("{\n.reg .pred p;\nmbarrier.try_wait.parity.shared::cta.b64 p, [%1], %2, %3;\nselp.b32 %0, 1, 0, p;\n}"
                   : "=r"(ok) : "r"(bar), "r"(parity), "r"(WAIT_NS) : "memory");
    else
      asm volatile("{\n.reg .pred p;\nmbarrier.try_wait.parity.shared::cta.b64 p, [%1], %2;\nselp.b32 %0, 1, 0, p;\n}"
                   : "=r"(ok) : "r"(bar), "r"(parity) : "memory");
    if (++spins > SPIN_LIMIT) break;
  } while (!ok);
}
__device__ __forceinline__ unsigned flag_read(const unsigned* p) {
  unsigned v;
  asm volatile("ld.relaxed.gpu.global.u32 %0, [%1];" : "=r"(v) : "l"(p) : "memory");
  return v;
}
__device__ __forceinline__ void flag_poll(const unsigned* p, unsigned target) {
  unsigned v;
  int spins = 0;
  do {
    if (POLL_NS && spins) __nanosleep(POLL_NS);
    asm volatile("ld.relaxed.gpu.global.u32 %0, [%1];" : "=r"(v) : "l"(p) : "memory");
    if (++spins > SPIN_LIMIT) break;
  } while ((int)(v - target) < 0);
}
__device__ __forceinline__ void flag_wait(const unsigned* p, unsigned target) {
  flag_poll(p, target);
  if (ACQ) asm volatile("fence.acquire.gpu;\nfence.proxy.async.global;" ::: "memory");
}
__device__ __forceinline__ void flag_signal(unsigned* p, int n, int lane) {
  if (lane == 0) asm volatile("fence.release.gpu;" ::: "memory");
  __syncwarp();
  if (lane < n) asm volatile("red.relaxed.gpu.global.add.u32 [%0], 1;" ::"l"(p + 32 * lane) : "memory");
}
__device__ __forceinline__ void flag_bump(unsigned* p) {
  asm volatile("red.relaxed.gpu.global.add.u32 [%0], 1;" ::"l"(p) : "memory");
}
__device__ __forceinline__ void fence_async_smem() { asm volatile("fence.proxy.async.shared::cta;" ::: "memory"); }
__device__ __forceinline__ void wg_sync(int id) { asm volatile("bar.sync %0, 128;" ::"r"(id) : "memory"); }

__device__ __forceinline__ void tma_2d(uint32_t dst, const CUtensorMap* tm, int c0, int c1, uint32_t bar) {
  asm volatile("cp.async.bulk.tensor.2d.shared::cluster.global.mbarrier::complete_tx::bytes [%0], [%1, {%3, %4}], [%2];"
               ::"r"(dst), "l"(tm), "r"(bar), "r"(c0), "r"(c1) : "memory");
}
__device__ __forceinline__ void tma_3d(uint32_t dst, const CUtensorMap* tm, int c0, int c1, int c2, uint32_t bar) {
  asm volatile("cp.async.bulk.tensor.3d.shared::cluster.global.mbarrier::complete_tx::bytes [%0], [%1, {%3, %4, %5}], [%2];"
               ::"r"(dst), "l"(tm), "r"(bar), "r"(c0), "r"(c1), "r"(c2) : "memory");
}
__device__ __forceinline__ void bulk_load(uint32_t dst, const void* src, uint32_t bytes, uint32_t bar) {
  asm volatile("cp.async.bulk.shared::cluster.global.mbarrier::complete_tx::bytes [%0], [%1], %2, [%3];"
               ::"r"(dst), "l"(src), "r"(bytes), "r"(bar) : "memory");
}
__device__ __forceinline__ void cp_async16(uint32_t dst, const void* src) {
  asm volatile("cp.async.cg.shared.global [%0], [%1], 16;" ::"r"(dst), "l"(src) : "memory");
}
__device__ __forceinline__ void tm_prefetch(const CUtensorMap* tm) {
  asm volatile("prefetch.tensormap [%0];" ::"l"(tm) : "memory");
}

__device__ __forceinline__ void wg_fence() { asm volatile("wgmma.fence.sync.aligned;" ::: "memory"); }
__device__ __forceinline__ void wg_commit() { asm volatile("wgmma.commit_group.sync.aligned;" ::: "memory"); }
template <int N> __device__ __forceinline__ void wg_wait() { asm volatile("wgmma.wait_group.sync.aligned %0;" ::"n"(N) : "memory"); }
__device__ __forceinline__ uint32_t desc_lo(uint32_t addr, uint32_t lbo) { return ((addr & 0x3FFFF) >> 4) | ((lbo >> 4) << 16); }
constexpr uint32_t desc_hi(uint32_t sbo, uint32_t swz) { return (sbo >> 4) | (swz << 30); }
constexpr uint32_t HI_SW128 = desc_hi(1024, 1), HI_SW64 = desc_hi(512, 2), HI_SW32 = desc_hi(256, 3), HI_NONE = desc_hi(128, 0);
template <int N> __device__ __forceinline__ void pin(float* d) {
#pragma unroll
  for (int i = 0; i < N; i++) asm volatile("" : "+f"(d[i])::"memory");
}

__device__ __forceinline__ uint32_t lds32(uint32_t a) {
  uint32_t v;
  asm volatile("ld.volatile.shared.u32 %0, [%1];" : "=r"(v) : "r"(a) : "memory");
  return v;
}
__device__ __forceinline__ uint4 ldg128(const void* a) {
  uint4 v;
  asm volatile("ld.global.nc.v4.u32 {%0, %1, %2, %3}, [%4];" : "=r"(v.x), "=r"(v.y), "=r"(v.z), "=r"(v.w) : "l"(a) : "memory");
  return v;
}
__device__ __forceinline__ uint2 ldg64(const void* a) {
  uint2 v;
  asm volatile("ld.global.nc.v2.u32 {%0, %1}, [%2];" : "=r"(v.x), "=r"(v.y) : "l"(a) : "memory");
  return v;
}
__device__ __forceinline__ void ldsm4(uint32_t* r, uint32_t a) {
  asm volatile("ldmatrix.sync.aligned.m8n8.x4.shared.b16 {%0, %1, %2, %3}, [%4];"
               : "=r"(r[0]), "=r"(r[1]), "=r"(r[2]), "=r"(r[3]) : "r"(a) : "memory");
}
__device__ __forceinline__ void ldsm4t(uint32_t* r, uint32_t a) {
  asm volatile("ldmatrix.sync.aligned.m8n8.x4.trans.shared.b16 {%0, %1, %2, %3}, [%4];"
               : "=r"(r[0]), "=r"(r[1]), "=r"(r[2]), "=r"(r[3]) : "r"(a) : "memory");
}
__device__ __forceinline__ uint4 lds128(uint32_t a) {
  uint4 v;
  asm volatile("ld.shared.v4.u32 {%0, %1, %2, %3}, [%4];" : "=r"(v.x), "=r"(v.y), "=r"(v.z), "=r"(v.w) : "r"(a) : "memory");
  return v;
}
__device__ __forceinline__ void sts128(uint32_t a, uint32_t x, uint32_t y, uint32_t z, uint32_t w) {
  asm volatile("st.shared.v4.u32 [%0], {%1, %2, %3, %4};" ::"r"(a), "r"(x), "r"(y), "r"(z), "r"(w) : "memory");
}
__device__ __forceinline__ void stsm4(uint32_t a, const uint32_t* r) {
  asm volatile("stmatrix.sync.aligned.m8n8.x4.shared.b16 [%0], {%1, %2, %3, %4};" ::"r"(a), "r"(r[0]), "r"(r[1]), "r"(r[2]), "r"(r[3]) : "memory");
}
__device__ __forceinline__ void stsm4t(uint32_t a, const uint32_t* r) {
  asm volatile("stmatrix.sync.aligned.m8n8.x4.trans.shared.b16 [%0], {%1, %2, %3, %4};" ::"r"(a), "r"(r[0]), "r"(r[1]), "r"(r[2]), "r"(r[3]) : "memory");
}
__device__ __forceinline__ uint32_t pack2(float lo, float hi) {
  uint32_t r;
  asm("cvt.rn.bf16x2.f32 %0, %1, %2;" : "=r"(r) : "f"(hi), "f"(lo));
  return r;
}
__device__ __forceinline__ uint32_t movm(uint32_t a) {
  uint32_t d;
  asm volatile("movmatrix.sync.aligned.m8n8.trans.b16 %0, %1;" : "=r"(d) : "r"(a));
  return d;
}
__device__ __forceinline__ uint32_t bmul(uint32_t a, uint32_t b) {
  uint32_t d;
  asm("mul.rn.bf16x2 %0, %1, %2;" : "=r"(d) : "r"(a), "r"(b));
  return d;
}
__device__ __forceinline__ uint32_t badd(uint32_t a, uint32_t b) {
  uint32_t d;
  asm("add.rn.bf16x2 %0, %1, %2;" : "=r"(d) : "r"(a), "r"(b));
  return d;
}
__device__ __forceinline__ float bf_lo(uint32_t x) { return __uint_as_float(x << 16); }
__device__ __forceinline__ float bf_hi(uint32_t x) { return __uint_as_float(x & 0xFFFF0000u); }
__device__ __forceinline__ float ex2(float x) {
  float y;
  asm("ex2.approx.ftz.f32 %0, %1;" : "=f"(y) : "f"(x));
  return y;
}
__device__ __forceinline__ float rcp(float x) {
  float y;
  asm("rcp.approx.ftz.f32 %0, %1;" : "=f"(y) : "f"(x));
  return y;
}
__device__ __forceinline__ void mma16816(float* d, uint32_t a0, uint32_t a1, uint32_t a2, uint32_t a3, uint32_t b0, uint32_t b1) {
  asm volatile("mma.sync.aligned.m16n8k16.row.col.f32.bf16.bf16.f32 {%0, %1, %2, %3}, {%4, %5, %6, %7}, {%8, %9}, {%0, %1, %2, %3};"
               : "+f"(d[0]), "+f"(d[1]), "+f"(d[2]), "+f"(d[3])
               : "r"(a0), "r"(a1), "r"(a2), "r"(a3), "r"(b0), "r"(b1));
}
__device__ __forceinline__ void mma1688(float* d, uint32_t a0, uint32_t a1, uint32_t b0) {
  asm volatile("mma.sync.aligned.m16n8k8.row.col.f32.bf16.bf16.f32 {%0, %1, %2, %3}, {%4, %5}, {%6}, {%0, %1, %2, %3};"
               : "+f"(d[0]), "+f"(d[1]), "+f"(d[2]), "+f"(d[3])
               : "r"(a0), "r"(a1), "r"(b0));
}

template <int N> struct WgRS;
template <int N> struct WgSST;
template <> struct WgRS<32> {
  template <uint32_t HB>
  static __device__ __forceinline__ void mma(float* d, const uint32_t* a, uint32_t db) {
    asm volatile("{\n.reg .pred p;\n.reg .b64 db;\nsetp.ne.b32 p, %22, 0;\n"
      "mov.b64 db, {%20, %21};\n"
      "wgmma.mma_async.sync.aligned.m64n32k16.f32.bf16.bf16 {"
      "%0, %1, %2, %3, %4, %5, %6, %7, %8, %9, %10, %11, %12, %13, %14, %15"
      "}, {%16, %17, %18, %19}, db, p, 1, 1, 1;\n}\n"
      : "+f"(d[0]), "+f"(d[1]), "+f"(d[2]), "+f"(d[3]), "+f"(d[4]), "+f"(d[5]), "+f"(d[6]), "+f"(d[7]),
        "+f"(d[8]), "+f"(d[9]), "+f"(d[10]), "+f"(d[11]), "+f"(d[12]), "+f"(d[13]), "+f"(d[14]), "+f"(d[15])
      : "r"(a[0]), "r"(a[1]), "r"(a[2]), "r"(a[3]), "r"(db), "n"(HB), "n"(1));
  }
  template <uint32_t HB>
  static __device__ __forceinline__ void set(float* d, const uint32_t* a, uint32_t db) {
    asm volatile("{\n.reg .pred p;\n.reg .b64 db;\nsetp.ne.b32 p, %22, 0;\n"
      "mov.b64 db, {%20, %21};\n"
      "wgmma.mma_async.sync.aligned.m64n32k16.f32.bf16.bf16 {"
      "%0, %1, %2, %3, %4, %5, %6, %7, %8, %9, %10, %11, %12, %13, %14, %15"
      "}, {%16, %17, %18, %19}, db, p, 1, 1, 1;\n}\n"
      : "=f"(d[0]), "=f"(d[1]), "=f"(d[2]), "=f"(d[3]), "=f"(d[4]), "=f"(d[5]), "=f"(d[6]), "=f"(d[7]),
        "=f"(d[8]), "=f"(d[9]), "=f"(d[10]), "=f"(d[11]), "=f"(d[12]), "=f"(d[13]), "=f"(d[14]), "=f"(d[15])
      : "r"(a[0]), "r"(a[1]), "r"(a[2]), "r"(a[3]), "r"(db), "n"(HB), "n"(0));
  }
};
template <> struct WgRS<64> {
  template <uint32_t HB>
  static __device__ __forceinline__ void mma(float* d, const uint32_t* a, uint32_t db) {
    asm volatile("{\n.reg .pred p;\n.reg .b64 db;\nsetp.ne.b32 p, %38, 0;\n"
      "mov.b64 db, {%36, %37};\n"
      "wgmma.mma_async.sync.aligned.m64n64k16.f32.bf16.bf16 {"
      "%0, %1, %2, %3, %4, %5, %6, %7, %8, %9, %10, %11, %12, %13, %14, %15, "
      "%16, %17, %18, %19, %20, %21, %22, %23, %24, %25, %26, %27, %28, %29, %30, %31"
      "}, {%32, %33, %34, %35}, db, p, 1, 1, 1;\n}\n"
      : "+f"(d[0]), "+f"(d[1]), "+f"(d[2]), "+f"(d[3]), "+f"(d[4]), "+f"(d[5]), "+f"(d[6]), "+f"(d[7]),
        "+f"(d[8]), "+f"(d[9]), "+f"(d[10]), "+f"(d[11]), "+f"(d[12]), "+f"(d[13]), "+f"(d[14]), "+f"(d[15]),
        "+f"(d[16]), "+f"(d[17]), "+f"(d[18]), "+f"(d[19]), "+f"(d[20]), "+f"(d[21]), "+f"(d[22]), "+f"(d[23]),
        "+f"(d[24]), "+f"(d[25]), "+f"(d[26]), "+f"(d[27]), "+f"(d[28]), "+f"(d[29]), "+f"(d[30]), "+f"(d[31])
      : "r"(a[0]), "r"(a[1]), "r"(a[2]), "r"(a[3]), "r"(db), "n"(HB), "n"(1));
  }
  template <uint32_t HB>
  static __device__ __forceinline__ void set(float* d, const uint32_t* a, uint32_t db) {
    asm volatile("{\n.reg .pred p;\n.reg .b64 db;\nsetp.ne.b32 p, %38, 0;\n"
      "mov.b64 db, {%36, %37};\n"
      "wgmma.mma_async.sync.aligned.m64n64k16.f32.bf16.bf16 {"
      "%0, %1, %2, %3, %4, %5, %6, %7, %8, %9, %10, %11, %12, %13, %14, %15, "
      "%16, %17, %18, %19, %20, %21, %22, %23, %24, %25, %26, %27, %28, %29, %30, %31"
      "}, {%32, %33, %34, %35}, db, p, 1, 1, 1;\n}\n"
      : "=f"(d[0]), "=f"(d[1]), "=f"(d[2]), "=f"(d[3]), "=f"(d[4]), "=f"(d[5]), "=f"(d[6]), "=f"(d[7]),
        "=f"(d[8]), "=f"(d[9]), "=f"(d[10]), "=f"(d[11]), "=f"(d[12]), "=f"(d[13]), "=f"(d[14]), "=f"(d[15]),
        "=f"(d[16]), "=f"(d[17]), "=f"(d[18]), "=f"(d[19]), "=f"(d[20]), "=f"(d[21]), "=f"(d[22]), "=f"(d[23]),
        "=f"(d[24]), "=f"(d[25]), "=f"(d[26]), "=f"(d[27]), "=f"(d[28]), "=f"(d[29]), "=f"(d[30]), "=f"(d[31])
      : "r"(a[0]), "r"(a[1]), "r"(a[2]), "r"(a[3]), "r"(db), "n"(HB), "n"(0));
  }
};
template <> struct WgSST<48> {
  template <uint32_t HA, uint32_t HB>
  static __device__ __forceinline__ void mma(float* d, uint32_t da, uint32_t db, int sc) {
    asm volatile("{\n.reg .pred p;\n.reg .b64 da, db;\nsetp.ne.b32 p, %28, 0;\n"
      "mov.b64 da, {%24, %25};\nmov.b64 db, {%26, %27};\n"
      "wgmma.mma_async.sync.aligned.m64n48k16.f32.bf16.bf16 {"
      "%0, %1, %2, %3, %4, %5, %6, %7, %8, %9, %10, %11, %12, %13, %14, %15, "
      "%16, %17, %18, %19, %20, %21, %22, %23"
      "}, da, db, p, 1, 1, 0, 1;\n}\n"
      : "+f"(d[0]), "+f"(d[1]), "+f"(d[2]), "+f"(d[3]), "+f"(d[4]), "+f"(d[5]), "+f"(d[6]), "+f"(d[7]),
        "+f"(d[8]), "+f"(d[9]), "+f"(d[10]), "+f"(d[11]), "+f"(d[12]), "+f"(d[13]), "+f"(d[14]), "+f"(d[15]),
        "+f"(d[16]), "+f"(d[17]), "+f"(d[18]), "+f"(d[19]), "+f"(d[20]), "+f"(d[21]), "+f"(d[22]), "+f"(d[23])
      : "r"(da), "n"(HA), "r"(db), "n"(HB), "r"(sc));
  }
};
template <> struct WgSST<80> {
  template <uint32_t HA, uint32_t HB>
  static __device__ __forceinline__ void mma(float* d, uint32_t da, uint32_t db, int sc) {
    asm volatile("{\n.reg .pred p;\n.reg .b64 da, db;\nsetp.ne.b32 p, %44, 0;\n"
      "mov.b64 da, {%40, %41};\nmov.b64 db, {%42, %43};\n"
      "wgmma.mma_async.sync.aligned.m64n80k16.f32.bf16.bf16 {"
      "%0, %1, %2, %3, %4, %5, %6, %7, %8, %9, %10, %11, %12, %13, %14, %15, "
      "%16, %17, %18, %19, %20, %21, %22, %23, %24, %25, %26, %27, %28, %29, %30, %31, "
      "%32, %33, %34, %35, %36, %37, %38, %39"
      "}, da, db, p, 1, 1, 0, 1;\n}\n"
      : "+f"(d[0]), "+f"(d[1]), "+f"(d[2]), "+f"(d[3]), "+f"(d[4]), "+f"(d[5]), "+f"(d[6]), "+f"(d[7]),
        "+f"(d[8]), "+f"(d[9]), "+f"(d[10]), "+f"(d[11]), "+f"(d[12]), "+f"(d[13]), "+f"(d[14]), "+f"(d[15]),
        "+f"(d[16]), "+f"(d[17]), "+f"(d[18]), "+f"(d[19]), "+f"(d[20]), "+f"(d[21]), "+f"(d[22]), "+f"(d[23]),
        "+f"(d[24]), "+f"(d[25]), "+f"(d[26]), "+f"(d[27]), "+f"(d[28]), "+f"(d[29]), "+f"(d[30]), "+f"(d[31]),
        "+f"(d[32]), "+f"(d[33]), "+f"(d[34]), "+f"(d[35]), "+f"(d[36]), "+f"(d[37]), "+f"(d[38]), "+f"(d[39])
      : "r"(da), "n"(HA), "r"(db), "n"(HB), "r"(sc));
  }
};
template <> struct WgSST<192> {
  template <uint32_t HA, uint32_t HB>
  static __device__ __forceinline__ void mma(float* d, uint32_t da, uint32_t db, int sc) {
    asm volatile("{\n.reg .pred p;\n.reg .b64 da, db;\nsetp.ne.b32 p, %100, 0;\n"
      "mov.b64 da, {%96, %97};\nmov.b64 db, {%98, %99};\n"
      "wgmma.mma_async.sync.aligned.m64n192k16.f32.bf16.bf16 {"
      "%0, %1, %2, %3, %4, %5, %6, %7, %8, %9, %10, %11, %12, %13, %14, %15, "
      "%16, %17, %18, %19, %20, %21, %22, %23, %24, %25, %26, %27, %28, %29, %30, %31, "
      "%32, %33, %34, %35, %36, %37, %38, %39, %40, %41, %42, %43, %44, %45, %46, %47, "
      "%48, %49, %50, %51, %52, %53, %54, %55, %56, %57, %58, %59, %60, %61, %62, %63, "
      "%64, %65, %66, %67, %68, %69, %70, %71, %72, %73, %74, %75, %76, %77, %78, %79, "
      "%80, %81, %82, %83, %84, %85, %86, %87, %88, %89, %90, %91, %92, %93, %94, %95"
      "}, da, db, p, 1, 1, 0, 1;\n}\n"
      : "+f"(d[0]), "+f"(d[1]), "+f"(d[2]), "+f"(d[3]), "+f"(d[4]), "+f"(d[5]), "+f"(d[6]), "+f"(d[7]),
        "+f"(d[8]), "+f"(d[9]), "+f"(d[10]), "+f"(d[11]), "+f"(d[12]), "+f"(d[13]), "+f"(d[14]), "+f"(d[15]),
        "+f"(d[16]), "+f"(d[17]), "+f"(d[18]), "+f"(d[19]), "+f"(d[20]), "+f"(d[21]), "+f"(d[22]), "+f"(d[23]),
        "+f"(d[24]), "+f"(d[25]), "+f"(d[26]), "+f"(d[27]), "+f"(d[28]), "+f"(d[29]), "+f"(d[30]), "+f"(d[31]),
        "+f"(d[32]), "+f"(d[33]), "+f"(d[34]), "+f"(d[35]), "+f"(d[36]), "+f"(d[37]), "+f"(d[38]), "+f"(d[39]),
        "+f"(d[40]), "+f"(d[41]), "+f"(d[42]), "+f"(d[43]), "+f"(d[44]), "+f"(d[45]), "+f"(d[46]), "+f"(d[47]),
        "+f"(d[48]), "+f"(d[49]), "+f"(d[50]), "+f"(d[51]), "+f"(d[52]), "+f"(d[53]), "+f"(d[54]), "+f"(d[55]),
        "+f"(d[56]), "+f"(d[57]), "+f"(d[58]), "+f"(d[59]), "+f"(d[60]), "+f"(d[61]), "+f"(d[62]), "+f"(d[63]),
        "+f"(d[64]), "+f"(d[65]), "+f"(d[66]), "+f"(d[67]), "+f"(d[68]), "+f"(d[69]), "+f"(d[70]), "+f"(d[71]),
        "+f"(d[72]), "+f"(d[73]), "+f"(d[74]), "+f"(d[75]), "+f"(d[76]), "+f"(d[77]), "+f"(d[78]), "+f"(d[79]),
        "+f"(d[80]), "+f"(d[81]), "+f"(d[82]), "+f"(d[83]), "+f"(d[84]), "+f"(d[85]), "+f"(d[86]), "+f"(d[87]),
        "+f"(d[88]), "+f"(d[89]), "+f"(d[90]), "+f"(d[91]), "+f"(d[92]), "+f"(d[93]), "+f"(d[94]), "+f"(d[95])
      : "r"(da), "n"(HA), "r"(db), "n"(HB), "r"(sc));
  }
};

struct FftConst {
  uint32_t f[2][4], fi[4][4];
  float ta[4], tb[4];
};
__device__ __forceinline__ void cis(int m, float scale, float& c, float& s) {
  const float a = (float)m * (-6.283185307179586f * scale);
  c = __cosf(a);
  s = __sinf(a);
}
__device__ __forceinline__ void fft_tables(uint32_t (&v)[12], int tw) {
  const int row = tw >> 2, ch = tw & 3;
#pragma unroll
  for (int i = 0; i < 4; i++) {
    float c[2], s[2], x[2];
#pragma unroll
    for (int e = 0; e < 2; e++) {
      cis((((32 * (8 * ch + 2 * i + e) + 15) * (4 * row - 63) + 2048) & 4095) - 2048, 1.f / 4096, c[e], s[e]);
      float gc, gs;
      cis((((row & 15) * (8 * (ch & 1) + 2 * i + e) + 8) & 15) - 8, 1.f / 16, gc, gs);
      x[e] = (row >> 4) == (ch >> 1) ? gc : (ch >> 1) ? gs : -gs;
    }
    v[i] = pack2(c[0] * 0.125f, c[1] * 0.125f);
    v[4 + i] = pack2(s[0] * 0.125f, s[1] * 0.125f);
    v[8 + i] = pack2(x[0], x[1]);
  }
#pragma unroll
  for (int i = 0; i < 12; i++) asm volatile("" : "+r"(v[i]));
}
__device__ __forceinline__ void fft_tables_store(const uint32_t (&v)[12], uint32_t sb, int tw) {
  const int row = tw >> 2;
  const uint32_t x = ((tw ^ (row >> 1)) & 3) << 4, a = sb + OFF_FT + (16 * (row >> 3) + (row & 7)) * 64 + x;
  sts128(a, v[0], v[1], v[2], v[3]);
  sts128(a + 512, v[4], v[5], v[6], v[7]);
  sts128(sb + OFF_GT + row * 64 + x, v[8], v[9], v[10], v[11]);
}
__device__ __forceinline__ void fft_twiddles(float (&v)[4], int tw) {
#pragma unroll
  for (int i = 0; i < 2; i++) {
    float c, s;
    cis((2 * (2 * (tw & 3) + i) - 15) * (4 * (tw >> 2) - 63), 1.f / 4096, c, s);
    v[2 * i] = __fdividef(-s, 1.f + c);
    v[2 * i + 1] = s;
  }
  pin<4>(v);
}
__device__ __forceinline__ void fft_matrices(FftConst& k, uint32_t sb, int w, int lane) {
  const uint32_t x = (lane >> 1) & 3;
  const uint4 t0 = lds128(sb + OFF_TT + 512 * w + 16 * lane), t1 = lds128(sb + OFF_TT + 512 * w + 16 * (lane ^ 3));
  k.ta[0] = __uint_as_float(t0.x); k.tb[0] = __uint_as_float(t0.y); k.ta[1] = __uint_as_float(t0.z); k.tb[1] = __uint_as_float(t0.w);
  k.ta[3] = __uint_as_float(t1.x); k.tb[3] = __uint_as_float(t1.y); k.ta[2] = __uint_as_float(t1.z); k.tb[2] = __uint_as_float(t1.w);
#pragma unroll
  for (int i = 0; i < 2; i++) {
    ldsm4(k.f[i], sb + OFF_FT + (16 * w + (lane & 15)) * 64 + (((2 * i + (lane >> 4)) ^ x) << 4));
    ldsm4t(k.fi[i], sb + OFF_FT + (32 * i + lane) * 64 + ((w ^ x) << 4));
#pragma unroll
    for (int j = 0; j < 4; j++) {
      k.fi[2 + i][j] = (j & 1) ? k.fi[i][j - 1] ^ 0x80008000u : k.fi[i][j + 1];
      asm volatile("" : "+r"(k.fi[2 + i][j]));
    }
  }
}
__device__ __forceinline__ void rot(bool inv, float& x, float& y, float a, float b) {
  x = fmaf(inv ? -a : a, y, x);
  y = fmaf(inv ? -b : b, x, y);
  x = fmaf(inv ? -a : a, y, x);
}
__device__ __forceinline__ void twiddle_fwd(uint32_t (&a)[4][4], float* d, const FftConst& k) {
#pragma unroll
  for (int q = 0; q < 4; q++)
#pragma unroll
    for (int j = 0; j < 2; j++) {
      float* x = d + 8 * q + 4 * j;
      rot(j, x[0], x[2], k.ta[2 * j], k.tb[2 * j]);
      rot(j, x[1], x[3], k.ta[2 * j + 1], k.tb[2 * j + 1]);
      a[q & 2][2 * j + (q & 1)] = pack2(x[0], x[1]);
      a[(q & 2) + 1][2 * j + (q & 1)] = pack2(x[2], x[3]);
    }
}
__device__ __forceinline__ void g_step(float* d, const uint32_t (&a)[4][4], uint32_t dre, uint32_t dim) {
  WgRS<32>::set<HI_SW64>(d, a[0], dre);
  WgRS<32>::set<HI_SW64>(d + 16, a[2], dre);
  WgRS<32>::mma<HI_SW64>(d, a[1], dim);
  WgRS<32>::mma<HI_SW64>(d + 16, a[3], dim);
  wg_commit();
}

__device__ __forceinline__ void conv_channel(const FftConst& k, uint32_t sb, int c, int wg, int w, int lane) {
  const uint32_t cb = sb + off_ch(c), bars = sb + OFF_BAR;
  const uint32_t du = desc_lo(cb, 1024), dg = desc_lo(sb + OFF_GT, 16), dz = desc_lo(cb + U_BYTES, 16);
  float U[32], H[32];
  uint32_t a[4][4], e[4][4];
  const float dv = __uint_as_float(lds32(sb + OFF_D + 4 * c));
  wg_fence();
  WgRS<64>::set<HI_SW32>(H, k.f[0], du + 256);
  WgRS<64>::mma<HI_SW32>(H, k.f[1], du + 256 + 32);
  wg_commit();
  wg_wait<0>();
  pin<32>(H);
  twiddle_fwd(a, H, k);
  if (ATT_GATE && H_EARLY) mbar_wait(bars + 8 * B_ATTN, 0);
  mbar_wait(bars + 8 * (B_U + (c < 3 ? c : 3)), 0);
  TSM(w == 0 && c < 3, 7 + wg);
  wg_fence();
  WgRS<64>::set<HI_SW32>(U, k.f[0], du);
  WgRS<64>::mma<HI_SW32>(U, k.f[1], du + 32);
  wg_commit();
  g_step(H, a, dg, dg + 64);
  wg_wait<1>();
  pin<32>(U);
  twiddle_fwd(e, U, k);
  wg_fence();
  g_step(U, e, dg, dg + 64);
  wg_wait<0>();
  pin<32>(U);
  pin<32>(H);
#pragma unroll
  for (int j = 0; j < 2; j++) {
    float pr[4][2], pi[4][2];
#pragma unroll
    for (int x = 0; x < 2; x++) {
      H[4 * j + x] += dv;
#pragma unroll
      for (int m = 0; m < 4; m++) {
#pragma unroll
        for (int q = 0; q <= m; q++) {
          const int ih = 16 * (q >> 1) + 2 * (q & 1) + 4 * j + x, iu = 16 * ((m - q) >> 1) + 2 * ((m - q) & 1) + 4 * j + x;
          pr[m][x] = q ? fmaf(H[ih], U[iu], pr[m][x]) : H[ih] * U[iu];
          pi[m][x] = q ? fmaf(H[ih], U[iu + 8], pi[m][x]) : H[ih] * U[iu + 8];
          pr[m][x] = fmaf(-H[ih + 8], U[iu + 8], pr[m][x]);
          pi[m][x] = fmaf(H[ih + 8], U[iu], pi[m][x]);
        }
      }
    }
#pragma unroll
    for (int m = 0; m < 4; m++) {
      a[m & 2][2 * j + (m & 1)] = pack2(pr[m][0], pr[m][1]);
      a[(m & 2) + 1][2 * j + (m & 1)] = pack2(pi[m][0], pi[m][1]);
    }
  }
  wg_fence();
  g_step(U, a, dg + 64, dg);
  const uint32_t za = cb + U_BYTES + (8 * w + (lane & 7)) * 128 + (((lane >> 3) ^ (lane & 7)) << 4);
  const uint32_t ya = cb + (lane >> 4) * 1024 + (8 * w + (lane & 7)) * 32 + ((((lane >> 3) ^ (lane >> 2)) & 1) << 4);
  wg_sync(1 + wg);
  wg_wait<0>();
  pin<32>(U);
  TSIF(w == 0, 80 + c);
#pragma unroll
  for (int p = 0; p < 2; p++) {
#pragma unroll
    for (int i = 0; i < 4; i++) {
      const int j = i & 1;
      float* x = U + 16 * p + 4 * j + (i & 2);
      rot(!j, x[8], x[0], k.ta[2 * j], k.tb[2 * j]);
      rot(!j, x[9], x[1], k.ta[2 * j + 1], k.tb[2 * j + 1]);
      e[p][i] = pack2(x[8], x[9]);
      e[2 + p][i] = pack2(x[0], x[1]);
    }
    stsm4(za ^ (64 * p), e[p]);
    stsm4((za ^ (64 * p)) + 4096, e[2 + p]);
  }
  fence_async_smem();
  wg_sync(1 + wg);
  wg_fence();
  WgRS<64>::set<HI_SW128>(H, k.fi[0], dz);
#pragma unroll
  for (int ks = 1; ks < 4; ks++) WgRS<64>::mma<HI_SW128>(H, k.fi[ks], dz + 128 * ks);
  wg_commit();
  wg_wait<0>();
  pin<32>(H);
  TSIF(w == 0, 88 + c);
#pragma unroll
  for (int j = 0; j < 8; j++)
    a[j >> 2][j & 3] = j < 2 ? pack2(H[4 * j], H[4 * j + 1]) : pack2(H[4 * j] + H[4 * j - 6], H[4 * j + 1] + H[4 * j - 5]);
  stsm4(ya, a[0]);
  stsm4(ya + 2048, a[1]);
  fence_async_smem();
  __syncwarp();
}

__device__ __forceinline__ void prep_slab(uint4* res, const uint2* sw, uint32_t sb, int slab, int w, int lane) {
  const int t = lane & 3, tp = (lane & 7) >> 1, pos = 8 * tp + 2 * (((lane >> 3) + tp) & 3) + (lane & 1);
  const uint32_t base = sb + OFF_KVS + slab * KVS_BYTES + pos * 128;
  uint32_t kk[2][4][4], vv[2][4];
  mbar_wait(sb + OFF_BAR + 8 * (B_KV + slab), 0);
#pragma unroll
  for (int h = 0; h < 2; h++) {
#pragma unroll
    for (int j = 0; j < 4; j++) {
      const uint32_t a = base + 128 * j;
      ldsm4t(kk[h][j], a + (((w + 4 * h) ^ ((a >> 7) & 7)) << 4));
    }
    const uint32_t a = base + KVS_V;
    ldsm4t(vv[h], a + (((w + 4 * h) ^ ((a >> 7) & 7)) << 4));
  }
#pragma unroll
  for (int h = 0; h < 2; h++) {
    uint32_t (&k)[4][4] = kk[h];
    uint32_t (&v)[4] = vv[h];
    const uint32_t w0 = __byte_perm(sw[h].x, 0, 0x1010), w1 = __byte_perm(sw[h].x, 0, 0x3232);
    const uint32_t w2 = __byte_perm(sw[h].y, 0, 0x1010), w3 = __byte_perm(sw[h].y, 0, 0x3232);
#pragma unroll
    for (int m = 0; m < 4; m++)
      v[m] = bmul(badd(badd(badd(bmul(k[0][m], w3), bmul(k[1][m], w2)), bmul(k[2][m], w1)), bmul(k[3][m], w0)), v[m]);
    uint32_t a[4];
#pragma unroll
    for (int m = 0; m < 4; m++) a[m] = (t & 1) ? v[(m + 3) & 3] : v[m];
    res[h] = (t & 2) ? make_uint4(a[2], a[3], a[0], a[1]) : make_uint4(a[0], a[1], a[2], a[3]);
  }
}

__device__ __forceinline__ void prep_gate(const Params& p, int b, int w, int lane) {
  uint2 gw[5], x[4][5];
#pragma unroll
  for (int j = 0; j < 5; j++) gw[j] = ldg64(reinterpret_cast<const uint2*>(p.gate_w) + lane + 32 * j);
#pragma unroll
  for (int i = 0; i < 4; i++)
#pragma unroll
    for (int j = 0; j < 5; j++)
      x[i][j] = ldg64(reinterpret_cast<const uint2*>(p.q) + (16 * b + 4 * w + i) * (DIM / 4) + lane + 32 * j);
  float s[4];
#pragma unroll
  for (int i = 0; i < 4; i++) {
    s[i] = 0.f;
#pragma unroll
    for (int j = 0; j < 5; j++) {
      const uint32_t m0 = bmul(x[i][j].x, gw[j].x), m1 = bmul(x[i][j].y, gw[j].y);
      s[i] += (bf_lo(m0) + bf_hi(m0)) + (bf_lo(m1) + bf_hi(m1));
    }
  }
  const bool h = lane & 16, q = lane & 8;
  const float a = (h ? s[2] : s[0]) + __shfl_xor_sync(0xffffffffu, h ? s[0] : s[2], 16);
  const float c = (h ? s[3] : s[1]) + __shfl_xor_sync(0xffffffffu, h ? s[1] : s[3], 16);
  float z = (q ? c : a) + __shfl_xor_sync(0xffffffffu, q ? a : c, 8);
#pragma unroll
  for (int o = 4; o > 0; o >>= 1) z += __shfl_xor_sync(0xffffffffu, z, o);
  z = bf_lo(pack2(z, 0.f));
  if ((lane & 7) == 0) g_gate[16 * b + 4 * w + (lane >> 3)] = bf_lo(pack2(__fdividef(1.f, 1.f + __expf(-z)), 0.f));
}

__device__ __forceinline__ uint32_t bmax(uint32_t a, uint32_t b) {
  uint32_t d;
  asm("max.bf16x2 %0, %1, %2;" : "=r"(d) : "r"(a), "r"(b));
  return d;
}
__device__ __forceinline__ void softmax_two(const float (&l)[2][2], uint32_t& p0, uint32_t& p1) {
  constexpr float kScale = 0.22360679774997896f, kLog2e = 1.4426950408889634f;
  const uint32_t r0 = pack2(l[0][0], l[1][0]), r1 = pack2(l[0][1], l[1][1]);
  const uint32_t x0 = pack2(bf_lo(r0) * kScale, bf_hi(r0) * kScale), x1 = pack2(bf_lo(r1) * kScale, bf_hi(r1) * kScale);
  uint32_t m = bmax(x0, x1);
  m = bmax(m, __shfl_xor_sync(0xffffffffu, m, 1));
  m = bmax(m, __shfl_xor_sync(0xffffffffu, m, 2));
  const float m0 = bf_lo(m) * kLog2e, m1 = bf_hi(m) * kLog2e;
  p0 = pack2(ex2(bf_lo(x0) * kLog2e - m0), ex2(bf_lo(x1) * kLog2e - m0));
  p1 = pack2(ex2(bf_hi(x0) * kLog2e - m1), ex2(bf_hi(x1) * kLog2e - m1));
}

__device__ __forceinline__ void halo_read(uint32_t (&kpv)[10], uint32_t (&vpv)[10], uint32_t (&tg)[7], const uint4* hp) {
#pragma unroll
  for (int j = 0; j < 7; j++) {
    uint32_t x0, x1, x2;
    asm volatile("ld.relaxed.gpu.global.v4.u32 {%0, %1, %2, %3}, [%4];"
                 : "=r"(x0), "=r"(x1), "=r"(x2), "=r"(tg[j]) : "l"(hp + 32 * j) : "memory");
    if (j < 4) kpv[3 * j] = x0; else vpv[3 * j - 10] = x0;
    if (j < 3) kpv[3 * j + 1] = x1; else vpv[3 * j - 9] = x1;
    if (j < 3) kpv[3 * j + 2] = x2; else if (j < 6) vpv[3 * j - 8] = x2;
  }
}

template <int ROT>
__device__ __forceinline__ void pack_qkv(const float* acc, uint32_t (&qlo)[10], uint32_t (&qhi)[10], uint32_t (&klo)[10],
                                         uint32_t (&khi)[10], uint32_t (&vlo)[10], uint32_t (&vhi)[10]) {
#pragma unroll
  for (int j = 0; j < 10; j++) {
    const int x = (j + ROT) % 10, tq = x < 8 ? x : 16 + x, tk = x < 8 ? 8 + x : 18 + x, tv = x < 8 ? 16 + x : 20 + x;
    khi[j] = pack2(acc[4 * tk + 2], acc[4 * tk + 3]);
    vhi[j] = movm(pack2(acc[4 * tv + 2], acc[4 * tv + 3]));
    qlo[j] = pack2(acc[4 * tq], acc[4 * tq + 1]);
    qhi[j] = pack2(acc[4 * tq + 2], acc[4 * tq + 3]);
    klo[j] = pack2(acc[4 * tk], acc[4 * tk + 1]);
    vlo[j] = pack2(acc[4 * tv], acc[4 * tv + 1]);
    asm volatile("" : "+r"(khi[j]), "+r"(qlo[j]), "+r"(qhi[j]), "+r"(klo[j]), "+r"(vlo[j]));
  }
}

template <int ROT> __device__ __forceinline__ void halo_send(const float* acc, uint4* ho, uint32_t tag) {
#pragma unroll
  for (int j = 0; j < 7; j++) {
    uint32_t x[3];
#pragma unroll
    for (int e = 0; e < 3; e++) {
      const int i = 3 * j + e, y = (i % 10 + ROT) % 10, tk = y < 8 ? 8 + y : 18 + y, tv = y < 8 ? 16 + y : 20 + y;
      x[e] = i < 10 ? pack2(acc[4 * tk + 2], acc[4 * tk + 3]) : i < 20 ? movm(pack2(acc[4 * tv + 2], acc[4 * tv + 3])) : 0u;
    }
    asm volatile("st.relaxed.gpu.global.v4.u32 [%0], {%1, %2, %3, %4};" ::"l"(ho + 32 * j), "r"(x[0]), "r"(x[1]), "r"(x[2]), "r"(tag) : "memory");
  }
}

__device__ __forceinline__ void attention(float* acc, uint32_t sb, int b, int par, int w, int lane, uint32_t tag) {
  const int g = lane >> 2, t = lane & 3;
  uint32_t klo[10], khi[10], vlo[10], vhi[10], qlo[10], qhi[10], kpv[10], vpv[10];
  if (HALO_FIRST && w == 3 && b < NCTA - 8) {
    uint4* ho = g_halo + (b * 2 + par) * 224 + lane;
    if (tail_first(b & 7)) halo_send<8>(acc, ho, tag);
    else halo_send<0>(acc, ho, tag);
    TSIF(par == 0, 76);
    pin<120>(acc);
  }
  if (tail_first(b & 7)) pack_qkv<8>(acc, qlo, qhi, klo, khi, vlo, vhi);
  else pack_qkv<0>(acc, qlo, qhi, klo, khi, vlo, vhi);
  const uint32_t xa = sb + OFF_KVX + (par * 3) * 2560 + lane * 16;
  if (w < 3) {
    sts128(xa + w * 2560, khi[0], khi[1], khi[2], khi[3]);
    sts128(xa + w * 2560 + 512, khi[4], khi[5], khi[6], khi[7]);
    sts128(xa + w * 2560 + 1024, khi[8], khi[9], vhi[0], vhi[1]);
    sts128(xa + w * 2560 + 1536, vhi[2], vhi[3], vhi[4], vhi[5]);
    sts128(xa + w * 2560 + 2048, vhi[6], vhi[7], vhi[8], vhi[9]);
  } else if (!HALO_FIRST && b < NCTA - 8) {
    uint4* ho = g_halo + (b * 2 + par) * 224 + lane;
#pragma unroll
    for (int j = 0; j < 7; j++) {
      const uint32_t x0 = j < 4 ? khi[3 * j] : vhi[3 * j - 10], x1 = j < 3 ? khi[3 * j + 1] : vhi[3 * j - 9];
      const uint32_t x2 = j < 3 ? khi[3 * j + 2] : j < 6 ? vhi[3 * j - 8] : 0u;
      asm volatile("st.relaxed.gpu.global.v4.u32 [%0], {%1, %2, %3, %4};" ::"l"(ho + 32 * j), "r"(x0), "r"(x1), "r"(x2), "r"(tag) : "memory");
    }
  }
  TSIF(par == 0 && w == 1, 64);
  TSIF(par == 0 && w == 3 && !HALO_FIRST, 76);
#pragma unroll
  for (int j = 0; j < 10; j++) vlo[j] = movm(vlo[j]);
  const bool far0 = 2 * t > g, far1 = 2 * t + 1 > g;
  const uint32_t mfar = (far0 ? 0x0000FFFFu : 0u) | (far1 ? 0xFFFF0000u : 0u);
  float slo[4][2], shi[4][2], lg[2][2];
  uint32_t phi[4], plo[4], qml[4], qmh[4];
#pragma unroll
  for (int h = 0; h < 4; h++) {
    const int f = h == 0 ? 0 : h == 1 ? 3 : h == 2 ? 5 : 8, hf = h < 2 ? 2 : 7;
    const bool mine = (h & 1) ? t >= 2 : t < 2;
    qml[h] = mine ? qlo[hf] : 0u;
    qmh[h] = mine ? qhi[hf] : 0u;
    float a[4] = {0.f, 0.f, 0.f, 0.f}, c[4] = {0.f, 0.f, 0.f, 0.f};
    mma16816(a, qlo[f], qhi[f], qlo[f + 1], qhi[f + 1], klo[f], klo[f + 1]);
    mma16816(c, qlo[f], qhi[f], qlo[f + 1], qhi[f + 1], khi[f], khi[f + 1]);
    mma1688(a, qml[h], qmh[h], klo[hf]);
    mma1688(c, qml[h], qmh[h], khi[hf]);
    slo[h][0] = a[0];
    slo[h][1] = a[1];
    shi[h][0] = lg[h & 1][0] = far0 ? a[2] : c[2];
    shi[h][1] = lg[h & 1][1] = far1 ? a[3] : c[3];
    if (!ATT_MERGE && (h & 1)) softmax_two(lg, phi[h - 1], phi[h]);
  }
  TSIF(par == 0 && w == 1, 65);
  wg_sync(1 + par);
  TSIF(par == 0 && w == 1, 66);
  const bool nohist = (w == 0) && (b < 8);
  const uint4* hp = g_halo + ((b - 8) * 2 + par) * 224 + lane;
  uint32_t tg[7];
  if (w > 0) {
    const uint4 v0 = lds128(xa + (w - 1) * 2560), v1 = lds128(xa + (w - 1) * 2560 + 512), v2 = lds128(xa + (w - 1) * 2560 + 1024);
    const uint4 v3 = lds128(xa + (w - 1) * 2560 + 1536), v4 = lds128(xa + (w - 1) * 2560 + 2048);
    kpv[0] = v0.x; kpv[1] = v0.y; kpv[2] = v0.z; kpv[3] = v0.w; kpv[4] = v1.x; kpv[5] = v1.y; kpv[6] = v1.z; kpv[7] = v1.w;
    kpv[8] = v2.x; kpv[9] = v2.y; vpv[0] = v2.z; vpv[1] = v2.w; vpv[2] = v3.x; vpv[3] = v3.y; vpv[4] = v3.z; vpv[5] = v3.w;
    vpv[6] = v4.x; vpv[7] = v4.y; vpv[8] = v4.z; vpv[9] = v4.w;
  } else if (nohist) {
#pragma unroll
    for (int j = 0; j < 10; j++) kpv[j] = vpv[j] = 0u;
  } else {
    TSIF(par == 0, 77);
    halo_read(kpv, vpv, tg, hp);
  }
  if (w == 0 && !nohist) {
    int spins = 0;
    while (true) {
      bool ok = true;
#pragma unroll
      for (int j = 0; j < 7; j++) ok = ok && tg[j] == tag;
      if (__all_sync(0xffffffffu, ok) || ++spins > SPIN_LIMIT) break;
      halo_read(kpv, vpv, tg, hp);
    }
    TSIF(par == 0, 79);
  }
#pragma unroll
  for (int h = 0; h < 4; h++) {
    const int f = h == 0 ? 0 : h == 1 ? 3 : h == 2 ? 5 : 8, hf = h < 2 ? 2 : 7;
    float a[4] = {0.f, 0.f, 0.f, 0.f};
    mma16816(a, qlo[f], qhi[f], qlo[f + 1], qhi[f + 1], kpv[f], kpv[f + 1]);
    mma1688(a, qml[h], qmh[h], kpv[hf]);
    const float ninf = __int_as_float(0xff800000);
    lg[h & 1][0] = far0 ? (nohist ? ninf : a[0]) : slo[h][0];
    lg[h & 1][1] = far1 ? (nohist ? ninf : a[1]) : slo[h][1];
    if (h & 1) {
      softmax_two(lg, plo[h - 1], plo[h]);
      if (ATT_MERGE) {
        const float lh[2][2] = {{shi[h - 1][0], shi[h - 1][1]}, {shi[h][0], shi[h][1]}};
        softmax_two(lh, phi[h - 1], phi[h]);
      }
    }
  }
  TSIF(par == 0 && w <= 1, 67 + w);
  uint32_t ov[20];
#pragma unroll
  for (int hp = 0; hp < 2; hp++) {
    const int hf = hp ? 7 : 2;
    float sh[4] = {0.f, 0.f, 0.f, 0.f}, i0 = 0.f, i1 = 0.f;
#pragma unroll
    for (int e = 0; e < 2; e++) {
      const int h = 2 * hp + e, f = h == 0 ? 0 : h == 1 ? 3 : h == 2 ? 5 : 8;
      const uint32_t a0 = plo[h] & mfar, a2 = plo[h] & ~mfar, a3 = phi[h] & mfar, c1 = phi[h] & ~mfar;
      float sum[4] = {0.f, 0.f, 0.f, 0.f};
      mma1688(sum, plo[h], phi[h], 0x3F803F80u);
      const float r0 = rcp(sum[0]), r1 = rcp(sum[2]);
#pragma unroll
      for (int j = f; j < f + 2; j++) {
        float o[4] = {0.f, 0.f, 0.f, 0.f};
        mma16816(o, a0, 0u, a2, a3, vpv[j], vlo[j]);
        mma1688(o, 0u, c1, vhi[j]);
        ov[2 * j] = pack2(o[0] * r0, o[1] * r0);
        ov[2 * j + 1] = pack2(o[2] * r1, o[3] * r1);
      }
      const bool mine = e ? g >= 4 : g < 4;
      mma16816(sh, a0, 0u, a2, a3, mine ? vpv[hf] : 0u, mine ? vlo[hf] : 0u);
      mma1688(sh, 0u, c1, mine ? vhi[hf] : 0u);
      if (e == 0 || t >= 2) {
        i0 = r0;
        i1 = r1;
      }
    }
    ov[2 * hf] = pack2(sh[0] * i0, sh[1] * i0);
    ov[2 * hf + 1] = pack2(sh[2] * i1, sh[3] * i1);
  }
  TS(32 + 4 * par + w);
  mbar_wait(sb + OFF_BAR + 8 * B_P1, 0);
  const uint32_t oa = sb + OFF_OA + (lane >> 4) * 2048 + (32 * w + 2 * (lane & 15) + par) * 16;
#pragma unroll
  for (int j = 0; j < 5; j++) stsm4(oa + 4096 * j, ov + 4 * j);
  TSIF(par == 0 && w == 0, 120);
  fence_async_smem();
  TSIF(par == 0 && w == 0, 121);
  __syncwarp();
  if (lane == 0) mbar_arrive(sb + OFF_BAR + 8 * B_ATTN);
  TSM(w == 0 || w == 2, 122 + par + (w == 2 ? 3 : 0));
}

struct Maps {
  CUtensorMap x, wm, wt, k, v, y, wo, qm, qt, om, ot, u;
};

__device__ __forceinline__ void load_stage(uint32_t sb, int kb, int b, const Maps& m) {
  const uint32_t st = sb + (kb & 3) * STAGE_BYTES, bar = sb + OFF_BAR + 8 * (B_FULL1 + (kb & 3));
  const int r = b >> 3, hg = b & 7, slab = kb - KV_KB;
  const bool kv = slab >= 0 && slab < 5;
  const uint32_t kbar = sb + OFF_BAR + 8 * (B_KV + slab), dst = sb + OFF_KVS + slab * KVS_BYTES;
  mbar_expect_tx(bar, STAGE_BYTES);
  if (kv) mbar_expect_tx(kbar, KVS_BYTES);
  tma_3d(st, &m.x, 64 * kb, 64 * r, 0, bar);
  if (kv && KV_MIX) tma_3d(dst, &m.k, 0, 32 * (b >> 1) - 3, 2 * slab + (b & 1), kbar);
  tma_3d(st + ST_W, &m.wm, 80 * hg + (tail_first(hg) ? 16 : 0), 64 * kb, 0, bar);
  if (kv && KV_MIX) tma_3d(dst + KVS_V, &m.v, 0, 32 * (b >> 1), 2 * slab + (b & 1), kbar);
  tma_3d(st + ST_WT, &m.wt, 80 * hg + (tail_first(hg) ? 0 : 64), 64 * kb, 0, bar);
  if (kv && !KV_MIX) tma_3d(dst, &m.k, 0, 32 * (b >> 1) - 3, 2 * slab + (b & 1), kbar);
  if (kv && !KV_MIX) tma_3d(dst + KVS_V, &m.v, 0, 32 * (b >> 1), 2 * slab + (b & 1), kbar);
}

__global__ void __launch_bounds__(NTHR, 1) fused_kernel(const __grid_constant__ Maps m, const Params p) {
  extern __shared__ __align__(1024) uint8_t smem[];
  const uint32_t sb = (uint32_t)__cvta_generic_to_shared(smem);
  const uint32_t bars = sb + OFF_BAR;
  const int tid = threadIdx.x, lane = tid & 31;
  int b = blockIdx.x;
  if (BMAP == 1) b = (((b & 63) >> 3) * 2 + (b & 1)) * 8 + (((b < 64 ? 0x6521 : 0x7430) >> (4 * ((b >> 1) & 3))) & 7);
  if (BMAP == 2) b = ((b & 63) >> 2) * 8 + (((b < 64 ? 0x6521 : 0x7430) >> (4 * (b & 3))) & 7);
  if (BMAP == 3) b = (((b & 63) >> 3) * 2 + (b & 1)) * 8 + (((b < 64 ? 0x7430 : 0x6521) >> (4 * ((b >> 1) & 3))) & 7);
  if (BMAP == 4) b = (((b >> 4) * 2 + (b & 1)) * 8) + ((b >> 1) & 7);
  if (BMAP == 5) b = 127 - b;
  const int r = b >> 3, hg = b & 7;

  if (CP0 && tid < 256) {
    const int row = tid >> 3, c = tid & 7;
    const uint32_t d = sb + row * 128 + ((c ^ (row & 7)) << 4);
    const char* xs = reinterpret_cast<const char*>(p.q) + (128 * r + 2 * row) * 1280 + 16 * c;
    const char* ws = reinterpret_cast<const char*>(p.wqkv) + row * 3840 + 160 * hg;
    const char* wm = ws + (tail_first(hg) ? 32 : 0) + 16 * c;
#pragma unroll
    for (int j = 0; j < 4; j++) cp_async16(d + 4096 * j, xs + (j >> 1) * 1280 + (j & 1) * 64 * 1280);
#pragma unroll
    for (int j = 0; j < 6; j++) cp_async16(d + ST_W + 4096 * j, wm + (j >> 1) * 1280 + (j & 1) * 32 * 3840);
    if (c < 6) {
#pragma unroll
      for (int j = 0; j < 2; j++)
        cp_async16(sb + ST_WT + (c >> 1) * 2048 + (row + 32 * j) * 32 + (((c ^ (row >> 2)) & 1) << 4),
                   ws + (tail_first(hg) ? 0 : 128) + (c >> 1) * 1280 + 16 * (c & 1) + j * 32 * 3840);
    }
    asm volatile("cp.async.commit_group;" ::: "memory");
  }
  if (tid == T_ISSUE) {
    TSM(true, 0);
#pragma unroll
    for (int i = 0; i < 4; i++) mbar_init(bars + 8 * (B_FULL1 + i), 1);
#pragma unroll
    for (int i = 0; i < 3; i++) mbar_init(bars + 8 * (B_KV + i), 1);
    fence_async_smem();
    if (CP0) mbar_arrive(bars + 8 * B_FULL1);
#pragma unroll 1
    for (int kb = CP0; kb <= PRE2; kb++) {
      load_stage(sb, kb, b, m);
      TS(85 + kb);
    }
  } else if (tid >= T_PF && tid < T_PF + 12) {
    tm_prefetch(&m.x + (tid - T_PF));
  } else if (tid == T_INIT) {
#pragma unroll
    for (int i = 0; i < 4; i++) mbar_init(bars + 8 * (B_EMPTY1 + i), 8);
#pragma unroll
    for (int i = 0; i < 8; i++) mbar_init(bars + 8 * (B_FULL2 + i), 1);
#pragma unroll
    for (int i = 0; i < 4; i++) mbar_init(bars + 8 * (B_EMPTY2 + i), 8);
#pragma unroll
    for (int i = 0; i < 4; i++) mbar_init(bars + 8 * (B_U + i), 1);
    mbar_init(bars + 8 * B_HA, 4);
    mbar_init(bars + 8 * B_GATE, 4);
    mbar_init(bars + 8 * B_HB, 1);
    mbar_init(bars + 8 * B_KVD, 4);
    mbar_init(bars + 8 * B_QF, 1);
    mbar_init(bars + 8 * B_ATTN, 8);
    mbar_init(bars + 8 * B_P1, 8);
    mbar_init(bars + 8 * B_C34, 1);
#pragma unroll
    for (int i = 0; i < 5; i++) mbar_init(bars + 8 * (B_YST + i), 4);
#pragma unroll
    for (int i = 0; i < 5; i++) mbar_init(bars + 8 * (B_US + i), 4);
    mbar_init(bars + 8 * B_YSIG, 1);
    mbar_init(bars + 8 * B_YFULL, 1);
    mbar_init(bars + 8 * B_EPOCH, 1);
    mbar_init(bars + 8 * B_PREP, 4);
    mbar_init(bars + 8 * B_USIG, 1);
    mbar_init(bars + 8 * B_WST, 1);
#pragma unroll
    for (int i = 3; i < 5; i++) mbar_init(bars + 8 * (B_KV + i), 1);
    mbar_init(bars + 8 * B_E3, 8);
    mbar_init(bars + 8 * B_LAST, 1);
    mbar_init(bars + 8 * B_OSIG, 1);
    mbar_init(bars + 8 * B_WOP, 1);
    fence_async_smem();
  }
  const int warp = __shfl_sync(0xffffffffu, tid >> 5, 0), wg = warp >> 2, w = warp & 3;
  __syncthreads();
  TSIF(tid == 0, 87);

  if (wg == 3) {
    asm volatile("setmaxnreg.dec.sync.aligned.u32 56;");
    if (w == 0) {
      if (lane == 0) {
#pragma unroll 1
        for (int kb = 1 + PRE2; kb < 10; kb++) {
          if (kb >= 4) mbar_wait(bars + 8 * (kb == 7 ? B_E3 : B_EMPTY1 + (kb & 3)), (kb >> 3) & 1);
          TSIF(kb >= 4, 44 + kb);
          load_stage(sb, kb, b, m);
          TSIF(kb == 3, 60);
          if (kb == TRIG_KB) mbar_arrive(bars + 8 * B_LAST);
        }
        mbar_wait(bars + 8 * B_WOP, 0);
        mbar_wait(bars + 8 * WL_TRIG, 0);
        mbar_wait(bars + 8 * B_EPOCH, 0);
        flag_wait(g_cnt + C_W + 32 * hg, (lds32(sb + OFF_EPOCH) + 1) * 16);
        TS(30);
#pragma unroll 1
        for (int j = 0; j < 8; j++) {
          if (j >= 6) mbar_wait(bars + 8 * (B_EMPTY2 + j - 6), 0);
          if (j == 4) mbar_wait(bars + 8 * B_ATTN, 0);
          TSIF(j >= 6, 100 + j);
          if (RF_GATE && j == 6) mbar_wait(bars + 8 * B_YSIG, 0);
          mbar_expect_tx(bars + 8 * (B_FULL2 + j), j == 0 ? WO_BYTES : j == 5 ? O_BYTES + WO_BYTES + 512 : O_BYTES + WO_BYTES);
          bulk_load(sb + off_w(j), g_WO + (hg * 8 + step_src(hg, j)) * 800, WO_BYTES, bars + 8 * (B_FULL2 + j));
        }
        mbar_wait(bars + 8 * (B_EMPTY2 + 3), 0);
        mbar_expect_tx(bars + 8 * B_QF, O_BYTES);
        tma_2d(sb + OFF_QS, &m.qm, 80 * hg, 128 * r, bars + 8 * B_QF);
        tma_2d(sb + OFF_QT, &m.qt, 80 * hg + 64, 128 * r, bars + 8 * B_QF);
      }
    } else if (w == 1) {
      unsigned epoch = 0;
      if (lane == 0) {
        epoch = atomicAdd(g_cnt + C_LAUNCH, 1u) / NCTA;
        asm volatile("st.shared.u32 [%0], %1;" ::"r"(sb + OFF_EPOCH), "r"(epoch) : "memory");
        mbar_arrive(bars + 8 * B_EPOCH);
        mbar_wait(bars + 8 * B_KVD, 0);
        mbar_expect_tx(bars + 8 * B_HB, 5 * 4096);
#pragma unroll 1
        for (int c = 0; c < 5; c++) {
          if (c == 3) mbar_wait(bars + 8 * B_S3, 0);
          bulk_load(sb + off_ch(c) + U_BYTES, p.ssm_k + (5 * b + c) * SEQ, 4096, bars + 8 * B_HB);
        }
#pragma unroll
        for (int c = 0; c < 4; c++) mbar_expect_tx(bars + 8 * (B_U + c), c < 3 ? U_BYTES : 2 * U_BYTES);
        const uint4* usrc = g_U + 5 * b * U_PITCH;
        mbar_wait(bars + 8 * B_USIG, 0);
        flag_wait(g_cnt + C_PREP + 32 * (b & 15), (epoch + 1) * NCTA);
        TS(23);
#pragma unroll
        for (int c = 0; c < 5; c++) {
          if (c == 3) mbar_wait(bars + 8 * (B_U + 2), 0);
          bulk_load(sb + off_ch(c), usrc + c * U_PITCH, U_BYTES, bars + 8 * (B_U + (c < 3 ? c : 3)));
          TSIF(c == 0 || c == 4, 116 + (c >> 2));
        }
      }
      epoch = __shfl_sync(0xffffffffu, epoch, 0);
      if (lane < 8) {
        const int src = (b & ~7) | step_src(hg, lane);
        mbar_wait(bars + 8 * B_OSIG, 0);
        TS(20);
        flag_wait(g_cnt + C_O + 32 * src, epoch + 1);
        if (lane >= 1 && lane < 4) bulk_load(sb + off_o(lane), g_O + src * 1280, O_BYTES, bars + 8 * (B_FULL2 + lane));
        __syncwarp(0xff);
        TS(21);
        if (lane == 5) bulk_load(sb + OFF_GATE, g_gate + 128 * r, 512, bars + 8 * (B_FULL2 + 5));
#pragma unroll 1
        for (int j = 4; j < 8; j++) {
          if (lane == j) {
            mbar_wait(bars + 8 * (j < 6 ? B_C34 : B_EMPTY2 + j - 6), 0);
            if (RF_GATE && j == 6) mbar_wait(bars + 8 * B_YSIG, 0);
            bulk_load(sb + off_o(j), g_O + src * 1280, O_BYTES, bars + 8 * (B_FULL2 + j));
          }
          __syncwarp(0xff);
        }
        TS(22);
      }
    } else if (w == 2) {
      mbar_wait(bars + 8 * B_PREP, 0);
      flag_signal(g_cnt + C_PREP, 16, lane);
      TS(25);
      if (lane == 0) mbar_arrive(bars + 8 * B_USIG);
      mbar_wait(bars + 8 * B_GATE, 0);
      if ((NOMB & 1) && lane == 0) asm volatile("fence.release.gpu;" ::: "memory");
      mbar_wait(bars + 8 * B_ATTN, 0);
      if (lane == 0) {
        if (O_DEFER) mbar_wait(bars + 8 * (B_U + 3), 0);
        asm volatile("cp.async.bulk.global.shared::cta.bulk_group [%0], [%1], 20480;\ncp.async.bulk.commit_group;\n"
                     "cp.async.bulk.wait_group 0;\nfence.proxy.async.global;" ::"l"(g_O + b * 1280), "r"(sb + OFF_OA) : "memory");
      }
      TS(74);
      if (!(NOMB & 1)) flag_signal(g_cnt + C_O + 32 * b, 1, lane);
      else if (lane == 0) flag_bump(g_cnt + C_O + 32 * b);
      TS(26);
      if (lane == 0) mbar_arrive(bars + 8 * B_OSIG);

    } else {
      if (lane == 0) {
        uint4* dst = g_WO + (hg * 8 + (r >> 1)) * 800 + (r & 1) * 80;
        mbar_wait(bars + 8 * B_P1, 0);
        mbar_wait(bars + 8 * WB_TRIG, 0);
        mbar_expect_tx(bars + 8 * B_WST, WO_BYTES / 2);
        tma_3d(sb + OFF_WS, &m.wo, 0, 40 * r, 5 * hg, bars + 8 * B_WST);
        mbar_wait(bars + 8 * B_WST, 0);
        mbar_wait(bars + 8 * WO_TRIG, 0);
#pragma unroll 1
        for (int n = 0; n < 5; n++)
          asm volatile("cp.async.bulk.global.shared::cta.bulk_group [%0], [%1], 1280;" ::"l"(dst + 160 * n), "r"(sb + OFF_WS + 1280 * n) : "memory");
        asm volatile("cp.async.bulk.commit_group;\ncp.async.bulk.wait_group 0;\nfence.proxy.async.global;" ::: "memory");
        if (!(NOMB & 4)) asm volatile("fence.release.gpu;" ::: "memory");
        flag_bump(g_cnt + C_W + 32 * hg);
        mbar_arrive(bars + 8 * B_WOP);
        TS(71);
#pragma unroll 1
        for (int c = 0; c < 5; c++) {
          mbar_wait(bars + 8 * (B_YST + c), 0);
          asm volatile("cp.async.bulk.global.shared::cta.bulk_group [%0], [%1], 4096;\ncp.async.bulk.commit_group;"
                       ::"l"(g_Y + (5 * b + c) * Y_PITCH), "r"(sb + off_ch(c)) : "memory");
          if (c == 2) {
            asm volatile("cp.async.bulk.wait_group.read 0;" ::: "memory");
            mbar_arrive(bars + 8 * B_C34);
          }
        }
        asm volatile("cp.async.bulk.wait_group 0;\nfence.proxy.async.global;" ::: "memory");
        TS(75);
        if (!(NOMB & 2)) asm volatile("fence.release.gpu;" ::: "memory");
        flag_bump(g_cnt + C_Y + 32 * (b >> 4));
        TS(27);
        mbar_arrive(bars + 8 * B_YSIG);
        mbar_expect_tx(bars + 8 * B_YFULL, 20480);
        flag_wait(g_cnt + C_Y + 32 * hg, (lds32(sb + OFF_EPOCH) + 1) * 16);
        TS(24);
        tma_2d(sb + OFF_YT, &m.y, 128 * r, 80 * hg, bars + 8 * B_YFULL);
        tma_2d(sb + OFF_YT + 10240, &m.y, 128 * r + 64, 80 * hg, bars + 8 * B_YFULL);
      }
    }
  } else {
    asm volatile("setmaxnreg.inc.sync.aligned.u32 152;");
    if (wg < 2) {
      float acc[120];
#pragma unroll
      for (int i = 0; i < 120; i++) acc[i] = 0.f;
      const uint32_t da = desc_lo(sb + wg * 8192, 16), db = desc_lo(sb + ST_W, 8192), dc = desc_lo(sb + ST_WT, 2048);
      if (PW1) pin<120>(acc);
      if (CP0) {
        asm volatile("cp.async.wait_group 0;" ::: "memory");
        fence_async_smem();
        asm volatile("bar.sync 4, 256;" ::: "memory");
      }
      if (PW1 == 2) mbar_wait(bars + 8 * B_FULL1, 0);
#pragma unroll 1
      for (int kb = 0; kb < 10; kb++) {
        mbar_wait(bars + 8 * (B_FULL1 + (kb & 3)), (kb >> 2) & 1);
        const uint32_t so = (kb & 3) * (STAGE_BYTES >> 4);
        wg_fence();
#pragma unroll
        for (int k = 0; k < 4; k++) {
          WgSST<192>::mma<HI_SW128, HI_SW128>(acc, da + so + 2 * k, db + so + 128 * k, 1);
          WgSST<48>::mma<HI_SW128, HI_SW32>(acc + 96, da + so + 2 * k, dc + so + 32 * k, 1);
        }
        wg_commit();
        wg_wait<1>();
        if (kb > 0 && lane == 0) mbar_arrive(bars + 8 * (kb == 4 ? B_E3 : B_EMPTY1 + ((kb - 1) & 3)));
      }
      mbar_wait(bars + 8 * B_EPOCH, 0);
      const uint32_t tag = lds32(sb + OFF_EPOCH) + 1;
      mbar_wait(bars + 8 * B_S3, 0);
      wg_wait<0>();
      pin<120>(acc);
      if (lane == 0) mbar_arrive(bars + 8 * B_P1);
      TSM(w == 0, 3 + wg);
      attention(acc, sb, b, wg, w, lane, tag);
    } else {
      const int tw = tid & 127, chl = 64 * (b & 1) + 8 * w + (lane >> 2);
      uint4* up = g_U + chl * U_PITCH + ((4 * (b >> 1) + (lane & 3)) ^ ((b >> 2) & 1));
      uint2 sw[10];
      uint32_t dv = 0;
      if (lane < 5) dv = __ldg(reinterpret_cast<const unsigned short*>(p.ssm_D) + 5 * b + lane);
#pragma unroll
      for (int i = 0; i < 10; i++) sw[i] = ldg64(reinterpret_cast<const uint2*>(p.shift_k) + chl + 128 * (i >> 1) + 32 * (i & 1));
      uint32_t tab[12];
      float tt[4];
      fft_tables(tab, tw);
      fft_twiddles(tt, tw);
      uint4 res[10];
#pragma unroll
      for (int i = 0; i < 10; i++) res[i] = make_uint4(0, 0, 0, 0);
#pragma unroll 1
      for (int slab = 0; slab < 5; slab++) {
#pragma unroll
        for (int i = 0; i < 8; i++) res[i] = res[i + 2];
        prep_slab(res + 8, sw, sb, slab, w, lane);
        TSIF(w == 0, 99 + 4 * slab);
#pragma unroll
        for (int i = 0; i < 8; i++) sw[i] = sw[i + 2];
      }
      TSIF(w == 0, 28);
      __syncwarp();
      if (lane == 0) mbar_arrive(bars + 8 * B_KVD + ((res[8].x ^ res[9].x) & p.zero));
      mbar_wait(bars + 8 * B_KVD, 0);
      fft_tables_store(tab, sb, tw);
      mbar_wait(bars + 8 * B_LAST, 0);
#pragma unroll
      for (int i = 0; i < 10; i++) up[(128 * (i >> 1) + 32 * (i & 1)) * U_PITCH] = res[i];
      __syncwarp();
      if (lane == 0) mbar_arrive(bars + 8 * B_PREP);
      TSIF(w == 0 && !U_TMA, 5);
      mbar_wait(bars + 8 * (G_AFTER ? B_USIG : B_LAST), 0);
      prep_gate(p, b, w, lane);
      __syncwarp();
      if (lane == 0) mbar_arrive(bars + 8 * B_GATE);
      TSIF(w == 0, 72);
      mbar_wait(bars + 8 * B_HB, 0);
      TSIF(w == 0, 2);
      const uint32_t ha = sb + U_BYTES + ((tw >> 3) * 16 + 8 + (tw & 7)) * 16;
      uint4 hv[5];
#pragma unroll
      for (int c = 0; c < 5; c++) hv[c] = lds128(ha + off_ch(c));
      __syncwarp();
#pragma unroll
      for (int c = 0; c < 5; c++) sts128((ha ^ 16) + off_ch(c), hv[c].x, hv[c].y, hv[c].z, hv[c].w);
      sts128(sb + OFF_TT + 16 * tw, __float_as_uint(tt[0]), __float_as_uint(tt[1]), __float_as_uint(tt[2]), __float_as_uint(tt[3]));
      if (tw < 5) asm volatile("st.shared.f32 [%0], %1;" ::"r"(sb + OFF_D + 4 * tw), "f"(bf_lo(dv) * 0.125f) : "memory");
      fence_async_smem();
      __syncwarp();
      if (lane == 0) mbar_arrive(bars + 8 * B_HA);
      TSIF(w == 0, 6);
    }

    FftConst fc;
    TSM(w == 0 && wg == 0, 104);
    mbar_wait(bars + 8 * B_HA, 0);
    fft_matrices(fc, sb, w, lane);
    TSM(w == 0 && wg == 0, 105);
    if (ATT_GATE && !H_EARLY) mbar_wait(bars + 8 * B_ATTN, 0);
    TSM(w == 0 && wg == 2, 124);
#pragma unroll 1
    for (uint32_t tasks = wg == 0 ? TASK0 : wg == 1 ? TASK1 : TASK2; tasks; tasks >>= 4) {
      const int c = (tasks & 7) - 1;
      conv_channel(fc, sb, c, wg, w, lane);
      if (lane == 0) mbar_arrive(bars + 8 * (B_YST + c));
      TSM(w == 0, 10 + c);
    }

    if (wg < 2) {
      const int g = lane >> 2;
      float acc[40];
#pragma unroll
      for (int i = 0; i < 40; i++) acc[i] = 0.f;
      const uint32_t da = desc_lo(sb + wg * 1024, 2048), db = desc_lo(sb, 2560);
      mbar_wait(bars + 8 * B_ATTN, 0);
      mbar_wait(bars + 8 * (B_YST + 3), 0);
      mbar_wait(bars + 8 * (B_YST + 4), 0);
      if (PW2) mbar_wait(bars + 8 * B_FULL2, 0);
      TSM(w == 0, 15 + wg);
#pragma unroll 1
      for (int j = 0; j < 8; j++) {
        mbar_wait(bars + 8 * (B_FULL2 + j), 0);
        const uint32_t oa = da + (off_o(j) >> 4), ob = db + (off_w(j) >> 4);
        wg_fence();
#pragma unroll
        for (int k = 0; k < 5; k++) WgSST<80>::mma<HI_NONE, HI_SW32>(acc, oa + 256 * k, ob + 32 * k, 1);
        wg_commit();
        wg_wait<1>();
        if (j >= 1 && j <= 4 && lane == 0) mbar_arrive(bars + 8 * (B_EMPTY2 + j - 1));
      }
      TSIF(w == 0 && wg == 0, 113);
      const int tr = 64 * wg + 16 * w + (lane & 15);
      const uint32_t fm = sb + OFF_QS + tr * 128, fx = (lane >> 4) ^ (tr & 7);
      const uint32_t ft = sb + OFF_QT + tr * 32 + (((lane >> 4) ^ (tr >> 2)) & 1) * 16;
      const float g0 = __uint_as_float(lds32(sb + OFF_GATE + (64 * wg + 16 * w + g) * 4));
      const float g1 = __uint_as_float(lds32(sb + OFF_GATE + (64 * wg + 16 * w + 8 + g) * 4));
      const uint32_t ga = pack2(g0, g0), gb = pack2(g1, g1);
      const uint32_t na = pack2(1.f - g0, 1.f - g0), nb = pack2(1.f - g1, 1.f - g1);

      wg_wait<0>();
      pin<40>(acc);
      TSM(w == 0, 17 + wg);
      uint32_t pb[20];
#pragma unroll
      for (int j = 0; j < 10; j++) {
        pb[2 * j] = bmul(na, pack2(acc[4 * j], acc[4 * j + 1]));
        pb[2 * j + 1] = bmul(nb, pack2(acc[4 * j + 2], acc[4 * j + 3]));
        asm volatile("" : "+r"(pb[2 * j]), "+r"(pb[2 * j + 1]));
      }
      const uint32_t ya = sb + OFF_YT + wg * 10240 + ((lane >> 4) * 8 + (lane & 7)) * 128 +
                          (((2 * w + (((lane >> 3) & 1) ^ wg)) ^ (lane & 7)) << 4);
      uint32_t qf[20];
      mbar_wait(bars + 8 * B_QF, 0);
#pragma unroll
      for (int j = 0; j < 5; j++) ldsm4(qf + 4 * j, j < 4 ? fm + ((fx ^ (2 * j)) << 4) : ft);
      mbar_wait(bars + 8 * B_YFULL, 0);
      TSM(w == 0 && wg == 0, 19);
#pragma unroll
      for (int j = 0; j < 5; j++) {
        uint32_t y[4];
        ldsm4t(y, ya + 2048 * j);
#pragma unroll
        for (int i = 0; i < 4; i++) qf[4 * j + i] = badd(bmul((i & 1) ? gb : ga, bmul(qf[4 * j + i], y[i])), pb[4 * j + i]);
      }
#pragma unroll
      for (int j = 0; j < 5; j++) stsm4(j < 4 ? fm + ((fx ^ (2 * j)) << 4) : ft, qf + 4 * j);
      fence_async_smem();
      __syncwarp();
      if (lane == 0) {
        const int row = 64 * wg + 16 * w;
        asm volatile("cp.async.bulk.tensor.2d.global.shared::cta.bulk_group [%0, {%2, %3}], [%1];"
                     ::"l"(&m.om), "r"(sb + OFF_QS + row * 128), "r"(80 * hg), "r"(128 * r + row) : "memory");
        asm volatile("cp.async.bulk.tensor.2d.global.shared::cta.bulk_group [%0, {%2, %3}], [%1];"
                     ::"l"(&m.ot), "r"(sb + OFF_QT + row * 32), "r"(80 * hg + 64), "r"(128 * r + row) : "memory");
        asm volatile("cp.async.bulk.commit_group;\ncp.async.bulk.wait_group.read 0;" ::: "memory");
      }
      TSM(true, 40 + 4 * wg + w);
      if (ENDBAR) asm volatile("bar.sync 15, 256;" ::: "memory");
    }
  }
}

typedef CUresult (*EncodeFn)(CUtensorMap*, CUtensorMapDataType, cuuint32_t, void*, const cuuint64_t*, const cuuint64_t*,
                             const cuuint32_t*, const cuuint32_t*, CUtensorMapInterleave, CUtensorMapSwizzle,
                             CUtensorMapL2promotion, CUtensorMapFloatOOBfill);

void encode(EncodeFn fn, CUtensorMap* tm, const void* base, int rank, const cuuint64_t* dims, const cuuint64_t* strides,
            const cuuint32_t* box, CUtensorMapSwizzle swz) {
  const cuuint32_t ones[3] = {1, 1, 1};
  fn(tm, CU_TENSOR_MAP_DATA_TYPE_BFLOAT16, rank, const_cast<void*>(base), dims, strides, box, ones,
     CU_TENSOR_MAP_INTERLEAVE_NONE, swz, CU_TENSOR_MAP_L2_PROMOTION_L2_128B, CU_TENSOR_MAP_FLOAT_OOB_FILL_NONE);
}

}

extern "C" void kernel_launch(void* const* d_in, const int* in_sizes, int n_in, void* d_out, int out_size) {
  (void)in_sizes; (void)n_in; (void)out_size;
  Params p;
  p.q = (const __nv_bfloat16*)d_in[0];
  p.k = (const __nv_bfloat16*)d_in[1];
  p.v = (const __nv_bfloat16*)d_in[2];
  p.shift_k = (const __nv_bfloat16*)d_in[3];
  p.ssm_k = (const __nv_bfloat16*)d_in[4];
  p.ssm_D = (const __nv_bfloat16*)d_in[5];
  p.wqkv = (const __nv_bfloat16*)d_in[7];
  p.wo = (const __nv_bfloat16*)d_in[8];
  p.gate_w = (const __nv_bfloat16*)d_in[9];
  p.out = (__nv_bfloat16*)d_out;
  p.zero = 0;

  static EncodeFn fn = nullptr;
  static void *yaddr = nullptr, *uaddr = nullptr;
  if (!fn) {
    cudaDriverEntryPointQueryResult qr;
    void* f = nullptr;
    cudaGetDriverEntryPoint("cuTensorMapEncodeTiled", &f, cudaEnableDefault, &qr);
    fn = (EncodeFn)f;
    cudaGetSymbolAddress(&yaddr, g_Y);
    cudaGetSymbolAddress(&uaddr, g_U);
    cudaFuncSetAttribute(fused_kernel, cudaFuncAttributeMaxDynamicSharedMemorySize, SMEM_BYTES);
  }
  Maps m;
  {
    const cuuint64_t dims[3] = {640, 1024, 2}, st[2] = {2560, 1280};
    const cuuint32_t box[3] = {64, 64, 2};
    encode(fn, &m.x, p.q, 3, dims, st, box, CU_TENSOR_MAP_SWIZZLE_128B);
  }
  {
    const cuuint64_t dims[3] = {640, 640, 3}, st[2] = {3840, 1280};
    const cuuint32_t box[3] = {64, 64, 3}, boxt[3] = {16, 64, 3};
    encode(fn, &m.wm, p.wqkv, 3, dims, st, box, CU_TENSOR_MAP_SWIZZLE_128B);
    encode(fn, &m.wt, p.wqkv, 3, dims, st, boxt, CU_TENSOR_MAP_SWIZZLE_32B);
  }
  {
    const cuuint64_t dims[3] = {64, 2048, 10}, st[2] = {1280, 128};
    const cuuint32_t boxk[3] = {64, 35, 1}, boxv[3] = {64, 32, 1};
    encode(fn, &m.k, p.k, 3, dims, st, boxk, CU_TENSOR_MAP_SWIZZLE_128B);
    encode(fn, &m.v, p.v, 3, dims, st, boxv, CU_TENSOR_MAP_SWIZZLE_128B);
  }
  {
    const cuuint64_t dims[3] = {16, 640, 40}, st[2] = {1280, 32};
    const cuuint32_t box[3] = {16, 40, 5};
    encode(fn, &m.wo, p.wo, 3, dims, st, box, CU_TENSOR_MAP_SWIZZLE_32B);
  }
  {
    const cuuint64_t dims[2] = {2048, 640}, st[1] = {Y_PITCH * 16};
    const cuuint32_t box[2] = {64, 80};
    encode(fn, &m.y, yaddr, 2, dims, st, box, CU_TENSOR_MAP_SWIZZLE_128B);
    const cuuint64_t stu[1] = {U_PITCH * 16};
    const cuuint32_t boxu[2] = {32, 64};
    encode(fn, &m.u, uaddr, 2, dims, stu, boxu, CU_TENSOR_MAP_SWIZZLE_NONE);
  }
  {
    const cuuint64_t dims[2] = {640, 2048}, st[1] = {1280};
    const cuuint32_t bqm[2] = {64, 128}, bqt[2] = {16, 128}, bom[2] = {64, 16}, bot[2] = {16, 16};
    encode(fn, &m.qm, p.q, 2, dims, st, bqm, CU_TENSOR_MAP_SWIZZLE_128B);
    encode(fn, &m.qt, p.q, 2, dims, st, bqt, CU_TENSOR_MAP_SWIZZLE_32B);
    encode(fn, &m.om, p.out, 2, dims, st, bom, CU_TENSOR_MAP_SWIZZLE_128B);
    encode(fn, &m.ot, p.out, 2, dims, st, bot, CU_TENSOR_MAP_SWIZZLE_32B);
  }
  fused_kernel<<<NCTA, NTHR, SMEM_BYTES>>>(m, p);
}
```

```cpp
#include <cuda.h>
#include <cuda_bf16.h>
#include <cuda_runtime.h>
#include <stdint.h>

namespace {

constexpr int SEQ = 2048, DIM = 640, NCTA = 128, NTHR = 512;

#define TRIG_KB 9
#define KV_KB 2
#define DEV_EXIT 0
#define ATT_GATE 1
#define G_AFTER 0
#define FENCE_LO 0
#define FENCE_HI 0
#define PW1 2
#define PW2 1
#define ENDBAR 0
#define PAD_KB 0
#define Y_ALIAS 1
#define H_EARLY 1
#define NOMB 0
#define SRC_ROT 0
#define WAIT_NS 0
#define WB_TRIG B_USIG
#define G_POS 0
#define TAILF 1
#define T_ISSUE 384
#define T_PF 416
#define T_INIT 448
#define ATT_MERGE 0
#define BMAP 1
#define PRE2 1
#define KV_MIX 0
#define O_DEFER 0
#define TASK0 0x52
#define TASK1 0x3
#define TASK2 0x41
#define HALO_FIRST 1
#define PREV_EARLY 0
#define ACQ 0
#define U_TMA 0
#define U_GATE 0
#define RF_GATE 0
#define WO_TRIG B_WST
#define WL_TRIG B_WOP
#define WO_GATE 1

constexpr uint32_t STAGE_BYTES = 47104, ST_W = 16384, ST_WT = 40960;
constexpr uint32_t O_BYTES = 20480, WO_BYTES = 12800;
constexpr uint32_t OFF_OA = 0;
constexpr uint32_t OFF_QS = 3 * O_BYTES, OFF_QT = OFF_QS + 16384;
constexpr uint32_t OFF_WC = 81920;
constexpr uint32_t OFF_WA = 94720;
constexpr uint32_t OFF_GATE = 145920;
constexpr uint32_t OFF_TT = 146432;
constexpr uint32_t OFF_KVX = 148480;
constexpr uint32_t OFF_CH3 = 163840;
constexpr uint32_t CH_BYTES = 12288, U_BYTES = 4096;
constexpr uint32_t OFF_FT = 225280, OFF_GT = 229376;
constexpr uint32_t OFF_CH0 = 188416;
constexpr uint32_t OFF_KVS = OFF_CH0, KVS_V = 4480, KVS_BYTES = 8576;
constexpr uint32_t OFF_WS = OFF_WA;
__device__ __forceinline__ uint32_t off_us(int s) { return OFF_CH0 + 4096 * ((0x65320 >> (4 * s)) & 7); }
constexpr uint32_t OFF_YT = 163840;
constexpr uint32_t OFF_BAR = 231936;
constexpr uint32_t SMEM_BYTES = OFF_BAR + 512;

enum : uint32_t {
  B_FULL1 = 0, B_EMPTY1 = 4, B_S3 = 7, B_FULL2 = 52, B_EMPTY2 = 13, B_U = 8, B_GATE = 12, B_HA = 19, B_HB = 20,
  B_ATTN = 21, B_C34 = 22, B_CONV = 23, B_YFULL = 24, B_EPOCH = 25, B_PREP = 26, B_P1 = 27, B_LAST = 28,
  B_E3 = 29, B_OSIG = 30, B_WOP = 31, B_USIG = 32, B_WST = 33, B_KV = 34, B_KVD = 39, B_QF = 17, B_YST = 40,
  B_US = 45, B_YSIG = 50
};
constexpr uint32_t OFF_EPOCH = OFF_BAR + 8 * 51, OFF_D = OFF_BAR + 8 * 60;
__device__ __forceinline__ uint32_t off_o(int j) { return j < 4 ? OFF_OA + j * O_BYTES : j < 6 ? OFF_CH0 + (j - 4) * O_BYTES : OFF_OA + (j - 6) * O_BYTES; }
__device__ __forceinline__ uint32_t off_w(int j) { return j < 4 ? OFF_WA + j * WO_BYTES : j == 4 ? OFF_KVX : j == 5 ? OFF_WC : OFF_WA + (j - 6) * WO_BYTES; }
__device__ __forceinline__ int step_src(int hg, int j) { return SRC_ROT ? (hg + j) & 7 : j == 0 ? hg : j <= hg ? j - 1 : j; }
__device__ __forceinline__ bool tail_first(int hg) { return TAILF && (hg & 3) == 3; }
__device__ __forceinline__ uint32_t off_ch(int c) { return (c < 3 ? OFF_CH0 : OFF_CH3 - 3 * CH_BYTES) + c * CH_BYTES; }

#define U_PITCH 264
__device__ __align__(1024) uint4 g_U[DIM * U_PITCH];
__device__ uint4 g_O[NCTA * 1280];
#define g_Y g_U
constexpr int Y_PITCH = U_PITCH;
__device__ uint4 g_WO[64 * 800];
__device__ uint4 g_halo[NCTA * 2 * 7 * 32];
__device__ float g_gate[SEQ + PAD_KB * 256];
__device__ unsigned g_cnt[32 * (1 + 2 * 16 + 8 + NCTA)];
constexpr int C_LAUNCH = 0, C_PREP = 32, C_Y = 32 * 17, C_W = 32 * 33, C_O = 32 * 41;

#define TSM(cond, slot) do { } while (0)
#define TSIF(cond, slot) do { if (__LINE__ >= FENCE_LO && __LINE__ < FENCE_HI) sched_fence(); } while (0)
__device__ __forceinline__ void sched_fence() {
  asm volatile("{\n.reg .pred p;\n.reg .u32 c;\nmov.u32 c, %%clock;\nsetp.eq.u32 p, c, 0;\n@p st.shared.u32 [%0], c;\n}"
               ::"r"(1024 + OFF_EPOCH + 4) : "memory");
}
#define TS(slot) TSIF(true, slot)

struct Params {
  const __nv_bfloat16 *q, *k, *v, *shift_k, *ssm_k, *ssm_D, *wqkv, *wo, *gate_w;
  __nv_bfloat16* out;
  uint32_t zero;
};

#define POLL_NS 0
constexpr int SPIN_LIMIT = 1 << 17;

__device__ __forceinline__ void mbar_init(uint32_t bar, uint32_t count) {
  asm volatile("mbarrier.init.shared::cta.b64 [%0], %1;" ::"r"(bar), "r"(count) : "memory");
}
__device__ __forceinline__ void mbar_expect_tx(uint32_t bar, uint32_t bytes) {
  asm volatile("mbarrier.arrive.expect_tx.shared::cta.b64 _, [%0], %1;" ::"r"(bar), "r"(bytes) : "memory");
}
__device__ __forceinline__ void mbar_arrive(uint32_t bar) {
  asm volatile("mbarrier.arrive.shared::cta.b64 _, [%0];" ::"r"(bar) : "memory");
}
__device__ __forceinline__ void mbar_wait(uint32_t bar, uint32_t parity) {
  uint32_t ok;
  int spins = 0;
  do {
    if (WAIT_NS)
      asm volatile("{\n.reg .pred p;\nmbarrier.try_wait.parity.shared::cta.b64 p, [%1], %2, %3;\nselp.b32 %0, 1, 0, p;\n}"
                   : "=r"(ok) : "r"(bar), "r"(parity), "r"(WAIT_NS) : "memory");
    else
      asm volatile("{\n.reg .pred p;\nmbarrier.try_wait.parity.shared::cta.b64 p, [%1], %2;\nselp.b32 %0, 1, 0, p;\n}"
                   : "=r"(ok) : "r"(bar), "r"(parity) : "memory");
    if (++spins > SPIN_LIMIT) break;
  } while (!ok);
}
__device__ __forceinline__ unsigned flag_read(const unsigned* p) {
  unsigned v;
  asm volatile("ld.relaxed.gpu.global.u32 %0, [%1];" : "=r"(v) : "l"(p) : "memory");
  return v;
}
__device__ __forceinline__ void flag_poll(const unsigned* p, unsigned target) {
  unsigned v;
  int spins = 0;
  do {
    if (POLL_NS && spins) __nanosleep(POLL_NS);
    asm volatile("ld.relaxed.gpu.global.u32 %0, [%1];" : "=r"(v) : "l"(p) : "memory");
    if (++spins > SPIN_LIMIT) break;
  } while ((int)(v - target) < 0);
}
__device__ __forceinline__ void flag_wait(const unsigned* p, unsigned target) {
  flag_poll(p, target);
  if (ACQ) asm volatile("fence.acquire.gpu;\nfence.proxy.async.global;" ::: "memory");
}
__device__ __forceinline__ void flag_signal(unsigned* p, int n, int lane) {
  if (lane == 0) asm volatile("fence.release.gpu;" ::: "memory");
  __syncwarp();
  if (lane < n) asm volatile("red.relaxed.gpu.global.add.u32 [%0], 1;" ::"l"(p + 32 * lane) : "memory");
}
__device__ __forceinline__ void flag_bump(unsigned* p) {
  asm volatile("red.relaxed.gpu.global.add.u32 [%0], 1;" ::"l"(p) : "memory");
}
__device__ __forceinline__ void fence_async_smem() { asm volatile("fence.proxy.async.shared::cta;" ::: "memory"); }
__device__ __forceinline__ void wg_sync(int id) { asm volatile("bar.sync %0, 128;" ::"r"(id) : "memory"); }

__device__ __forceinline__ void tma_2d(uint32_t dst, const CUtensorMap* tm, int c0, int c1, uint32_t bar) {
  asm volatile("cp.async.bulk.tensor.2d.shared::cluster.global.mbarrier::complete_tx::bytes [%0], [%1, {%3, %4}], [%2];"
               ::"r"(dst), "l"(tm), "r"(bar), "r"(c0), "r"(c1) : "memory");
}
__device__ __forceinline__ void tma_3d(uint32_t dst, const CUtensorMap* tm, int c0, int c1, int c2, uint32_t bar) {
  asm volatile("cp.async.bulk.tensor.3d.shared::cluster.global.mbarrier::complete_tx::bytes [%0], [%1, {%3, %4, %5}], [%2];"
               ::"r"(dst), "l"(tm), "r"(bar), "r"(c0), "r"(c1), "r"(c2) : "memory");
}
__device__ __forceinline__ void bulk_load(uint32_t dst, const void* src, uint32_t bytes, uint32_t bar) {
  asm volatile("cp.async.bulk.shared::cluster.global.mbarrier::complete_tx::bytes [%0], [%1], %2, [%3];"
               ::"r"(dst), "l"(src), "r"(bytes), "r"(bar) : "memory");
}
__device__ __forceinline__ void tm_prefetch(const CUtensorMap* tm) {
  asm volatile("prefetch.tensormap [%0];" ::"l"(tm) : "memory");
}

__device__ __forceinline__ void wg_fence() { asm volatile("wgmma.fence.sync.aligned;" ::: "memory"); }
__device__ __forceinline__ void wg_commit() { asm volatile("wgmma.commit_group.sync.aligned;" ::: "memory"); }
template <int N> __device__ __forceinline__ void wg_wait() { asm volatile("wgmma.wait_group.sync.aligned %0;" ::"n"(N) : "memory"); }
__device__ __forceinline__ uint32_t desc_lo(uint32_t addr, uint32_t lbo) { return ((addr & 0x3FFFF) >> 4) | ((lbo >> 4) << 16); }
constexpr uint32_t desc_hi(uint32_t sbo, uint32_t swz) { return (sbo >> 4) | (swz << 30); }
constexpr uint32_t HI_SW128 = desc_hi(1024, 1), HI_SW64 = desc_hi(512, 2), HI_SW32 = desc_hi(256, 3), HI_NONE = desc_hi(128, 0);
template <int N> __device__ __forceinline__ void pin(float* d) {
#pragma unroll
  for (int i = 0; i < N; i++) asm volatile("" : "+f"(d[i])::"memory");
}

__device__ __forceinline__ uint32_t lds32(uint32_t a) {
  uint32_t v;
  asm volatile("ld.volatile.shared.u32 %0, [%1];" : "=r"(v) : "r"(a) : "memory");
  return v;
}
__device__ __forceinline__ uint4 ldg128(const void* a) {
  uint4 v;
  asm volatile("ld.global.nc.v4.u32 {%0, %1, %2, %3}, [%4];" : "=r"(v.x), "=r"(v.y), "=r"(v.z), "=r"(v.w) : "l"(a) : "memory");
  return v;
}
__device__ __forceinline__ uint2 ldg64(const void* a) {
  uint2 v;
  asm volatile("ld.global.nc.v2.u32 {%0, %1}, [%2];" : "=r"(v.x), "=r"(v.y) : "l"(a) : "memory");
  return v;
}
__device__ __forceinline__ void ldsm4(uint32_t* r, uint32_t a) {
  asm volatile("ldmatrix.sync.aligned.m8n8.x4.shared.b16 {%0, %1, %2, %3}, [%4];"
               : "=r"(r[0]), "=r"(r[1]), "=r"(r[2]), "=r"(r[3]) : "r"(a) : "memory");
}
__device__ __forceinline__ void ldsm4t(uint32_t* r, uint32_t a) {
  asm volatile("ldmatrix.sync.aligned.m8n8.x4.trans.shared.b16 {%0, %1, %2, %3}, [%4];"
               : "=r"(r[0]), "=r"(r[1]), "=r"(r[2]), "=r"(r[3]) : "r"(a) : "memory");
}
__device__ __forceinline__ uint4 lds128(uint32_t a) {
  uint4 v;
  asm volatile("ld.shared.v4.u32 {%0, %1, %2, %3}, [%4];" : "=r"(v.x), "=r"(v.y), "=r"(v.z), "=r"(v.w) : "r"(a) : "memory");
  return v;
}
__device__ __forceinline__ void sts128(uint32_t a, uint32_t x, uint32_t y, uint32_t z, uint32_t w) {
  asm volatile("st.shared.v4.u32 [%0], {%1, %2, %3, %4};" ::"r"(a), "r"(x), "r"(y), "r"(z), "r"(w) : "memory");
}
__device__ __forceinline__ void stsm4(uint32_t a, const uint32_t* r) {
  asm volatile("stmatrix.sync.aligned.m8n8.x4.shared.b16 [%0], {%1, %2, %3, %4};" ::"r"(a), "r"(r[0]), "r"(r[1]), "r"(r[2]), "r"(r[3]) : "memory");
}
__device__ __forceinline__ void stsm4t(uint32_t a, const uint32_t* r) {
  asm volatile("stmatrix.sync.aligned.m8n8.x4.trans.shared.b16 [%0], {%1, %2, %3, %4};" ::"r"(a), "r"(r[0]), "r"(r[1]), "r"(r[2]), "r"(r[3]) : "memory");
}
__device__ __forceinline__ uint32_t pack2(float lo, float hi) {
  uint32_t r;
  asm("cvt.rn.bf16x2.f32 %0, %1, %2;" : "=r"(r) : "f"(hi), "f"(lo));
  return r;
}
__device__ __forceinline__ uint32_t movm(uint32_t a) {
  uint32_t d;
  asm volatile("movmatrix.sync.aligned.m8n8.trans.b16 %0, %1;" : "=r"(d) : "r"(a));
  return d;
}
__device__ __forceinline__ uint32_t bmul(uint32_t a, uint32_t b) {
  uint32_t d;
  asm("mul.rn.bf16x2 %0, %1, %2;" : "=r"(d) : "r"(a), "r"(b));
  return d;
}
__device__ __forceinline__ uint32_t badd(uint32_t a, uint32_t b) {
  uint32_t d;
  asm("add.rn.bf16x2 %0, %1, %2;" : "=r"(d) : "r"(a), "r"(b));
  return d;
}
__device__ __forceinline__ float bf_lo(uint32_t x) { return __uint_as_float(x << 16); }
__device__ __forceinline__ float bf_hi(uint32_t x) { return __uint_as_float(x & 0xFFFF0000u); }
__device__ __forceinline__ float ex2(float x) {
  float y;
  asm("ex2.approx.ftz.f32 %0, %1;" : "=f"(y) : "f"(x));
  return y;
}
__device__ __forceinline__ float rcp(float x) {
  float y;
  asm("rcp.approx.ftz.f32 %0, %1;" : "=f"(y) : "f"(x));
  return y;
}
__device__ __forceinline__ void mma16816(float* d, uint32_t a0, uint32_t a1, uint32_t a2, uint32_t a3, uint32_t b0, uint32_t b1) {
  asm volatile("mma.sync.aligned.m16n8k16.row.col.f32.bf16.bf16.f32 {%0, %1, %2, %3}, {%4, %5, %6, %7}, {%8, %9}, {%0, %1, %2, %3};"
               : "+f"(d[0]), "+f"(d[1]), "+f"(d[2]), "+f"(d[3])
               : "r"(a0), "r"(a1), "r"(a2), "r"(a3), "r"(b0), "r"(b1));
}
__device__ __forceinline__ void mma1688(float* d, uint32_t a0, uint32_t a1, uint32_t b0) {
  asm volatile("mma.sync.aligned.m16n8k8.row.col.f32.bf16.bf16.f32 {%0, %1, %2, %3}, {%4, %5}, {%6}, {%0, %1, %2, %3};"
               : "+f"(d[0]), "+f"(d[1]), "+f"(d[2]), "+f"(d[3])
               : "r"(a0), "r"(a1), "r"(b0));
}

template <int N> struct WgRS;
template <int N> struct WgSST;
template <> struct WgRS<32> {
  template <uint32_t HB>
  static __device__ __forceinline__ void mma(float* d, const uint32_t* a, uint32_t db) {
    asm volatile("{\n.reg .pred p;\n.reg .b64 db;\nsetp.ne.b32 p, %22, 0;\n"
      "mov.b64 db, {%20, %21};\n"
      "wgmma.mma_async.sync.aligned.m64n32k16.f32.bf16.bf16 {"
      "%0, %1, %2, %3, %4, %5, %6, %7, %8, %9, %10, %11, %12, %13, %14, %15"
      "}, {%16, %17, %18, %19}, db, p, 1, 1, 1;\n}\n"
      : "+f"(d[0]), "+f"(d[1]), "+f"(d[2]), "+f"(d[3]), "+f"(d[4]), "+f"(d[5]), "+f"(d[6]), "+f"(d[7]),
        "+f"(d[8]), "+f"(d[9]), "+f"(d[10]), "+f"(d[11]), "+f"(d[12]), "+f"(d[13]), "+f"(d[14]), "+f"(d[15])
      : "r"(a[0]), "r"(a[1]), "r"(a[2]), "r"(a[3]), "r"(db), "n"(HB), "n"(1));
  }
  template <uint32_t HB>
  static __device__ __forceinline__ void set(float* d, const uint32_t* a, uint32_t db) {
    asm volatile("{\n.reg .pred p;\n.reg .b64 db;\nsetp.ne.b32 p, %22, 0;\n"
      "mov.b64 db, {%20, %21};\n"
      "wgmma.mma_async.sync.aligned.m64n32k16.f32.bf16.bf16 {"
      "%0, %1, %2, %3, %4, %5, %6, %7, %8, %9, %10, %11, %12, %13, %14, %15"
      "}, {%16, %17, %18, %19}, db, p, 1, 1, 1;\n}\n"
      : "=f"(d[0]), "=f"(d[1]), "=f"(d[2]), "=f"(d[3]), "=f"(d[4]), "=f"(d[5]), "=f"(d[6]), "=f"(d[7]),
        "=f"(d[8]), "=f"(d[9]), "=f"(d[10]), "=f"(d[11]), "=f"(d[12]), "=f"(d[13]), "=f"(d[14]), "=f"(d[15])
      : "r"(a[0]), "r"(a[1]), "r"(a[2]), "r"(a[3]), "r"(db), "n"(HB), "n"(0));
  }
};
template <> struct WgRS<64> {
  template <uint32_t HB>
  static __device__ __forceinline__ void mma(float* d, const uint32_t* a, uint32_t db) {
    asm volatile("{\n.reg .pred p;\n.reg .b64 db;\nsetp.ne.b32 p, %38, 0;\n"
      "mov.b64 db, {%36, %37};\n"
      "wgmma.mma_async.sync.aligned.m64n64k16.f32.bf16.bf16 {"
      "%0, %1, %2, %3, %4, %5, %6, %7, %8, %9, %10, %11, %12, %13, %14, %15, "
      "%16, %17, %18, %19, %20, %21, %22, %23, %24, %25, %26, %27, %28, %29, %30, %31"
      "}, {%32, %33, %34, %35}, db, p, 1, 1, 1;\n}\n"
      : "+f"(d[0]), "+f"(d[1]), "+f"(d[2]), "+f"(d[3]), "+f"(d[4]), "+f"(d[5]), "+f"(d[6]), "+f"(d[7]),
        "+f"(d[8]), "+f"(d[9]), "+f"(d[10]), "+f"(d[11]), "+f"(d[12]), "+f"(d[13]), "+f"(d[14]), "+f"(d[15]),
        "+f"(d[16]), "+f"(d[17]), "+f"(d[18]), "+f"(d[19]), "+f"(d[20]), "+f"(d[21]), "+f"(d[22]), "+f"(d[23]),
        "+f"(d[24]), "+f"(d[25]), "+f"(d[26]), "+f"(d[27]), "+f"(d[28]), "+f"(d[29]), "+f"(d[30]), "+f"(d[31])
      : "r"(a[0]), "r"(a[1]), "r"(a[2]), "r"(a[3]), "r"(db), "n"(HB), "n"(1));
  }
  template <uint32_t HB>
  static __device__ __forceinline__ void set(float* d, const uint32_t* a, uint32_t db) {
    asm volatile("{\n.reg .pred p;\n.reg .b64 db;\nsetp.ne.b32 p, %38, 0;\n"
      "mov.b64 db, {%36, %37};\n"
      "wgmma.mma_async.sync.aligned.m64n64k16.f32.bf16.bf16 {"
      "%0, %1, %2, %3, %4, %5, %6, %7, %8, %9, %10, %11, %12, %13, %14, %15, "
      "%16, %17, %18, %19, %20, %21, %22, %23, %24, %25, %26, %27, %28, %29, %30, %31"
      "}, {%32, %33, %34, %35}, db, p, 1, 1, 1;\n}\n"
      : "=f"(d[0]), "=f"(d[1]), "=f"(d[2]), "=f"(d[3]), "=f"(d[4]), "=f"(d[5]), "=f"(d[6]), "=f"(d[7]),
        "=f"(d[8]), "=f"(d[9]), "=f"(d[10]), "=f"(d[11]), "=f"(d[12]), "=f"(d[13]), "=f"(d[14]), "=f"(d[15]),
        "=f"(d[16]), "=f"(d[17]), "=f"(d[18]), "=f"(d[19]), "=f"(d[20]), "=f"(d[21]), "=f"(d[22]), "=f"(d[23]),
        "=f"(d[24]), "=f"(d[25]), "=f"(d[26]), "=f"(d[27]), "=f"(d[28]), "=f"(d[29]), "=f"(d[30]), "=f"(d[31])
      : "r"(a[0]), "r"(a[1]), "r"(a[2]), "r"(a[3]), "r"(db), "n"(HB), "n"(0));
  }
};
template <> struct WgSST<48> {
  template <uint32_t HA, uint32_t HB>
  static __device__ __forceinline__ void mma(float* d, uint32_t da, uint32_t db, int sc) {
    asm volatile("{\n.reg .pred p;\n.reg .b64 da, db;\nsetp.ne.b32 p, %28, 0;\n"
      "mov.b64 da, {%24, %25};\nmov.b64 db, {%26, %27};\n"
      "wgmma.mma_async.sync.aligned.m64n48k16.f32.bf16.bf16 {"
      "%0, %1, %2, %3, %4, %5, %6, %7, %8, %9, %10, %11, %12, %13, %14, %15, "
      "%16, %17, %18, %19, %20, %21, %22, %23"
      "}, da, db, p, 1, 1, 0, 1;\n}\n"
      : "+f"(d[0]), "+f"(d[1]), "+f"(d[2]), "+f"(d[3]), "+f"(d[4]), "+f"(d[5]), "+f"(d[6]), "+f"(d[7]),
        "+f"(d[8]), "+f"(d[9]), "+f"(d[10]), "+f"(d[11]), "+f"(d[12]), "+f"(d[13]), "+f"(d[14]), "+f"(d[15]),
        "+f"(d[16]), "+f"(d[17]), "+f"(d[18]), "+f"(d[19]), "+f"(d[20]), "+f"(d[21]), "+f"(d[22]), "+f"(d[23])
      : "r"(da), "n"(HA), "r"(db), "n"(HB), "r"(sc));
  }
};
template <> struct WgSST<80> {
  template <uint32_t HA, uint32_t HB>
  static __device__ __forceinline__ void mma(float* d, uint32_t da, uint32_t db, int sc) {
    asm volatile("{\n.reg .pred p;\n.reg .b64 da, db;\nsetp.ne.b32 p, %44, 0;\n"
      "mov.b64 da, {%40, %41};\nmov.b64 db, {%42, %43};\n"
      "wgmma.mma_async.sync.aligned.m64n80k16.f32.bf16.bf16 {"
      "%0, %1, %2, %3, %4, %5, %6, %7, %8, %9, %10, %11, %12, %13, %14, %15, "
      "%16, %17, %18, %19, %20, %21, %22, %23, %24, %25, %26, %27, %28, %29, %30, %31, "
      "%32, %33, %34, %35, %36, %37, %38, %39"
      "}, da, db, p, 1, 1, 0, 1;\n}\n"
      : "+f"(d[0]), "+f"(d[1]), "+f"(d[2]), "+f"(d[3]), "+f"(d[4]), "+f"(d[5]), "+f"(d[6]), "+f"(d[7]),
        "+f"(d[8]), "+f"(d[9]), "+f"(d[10]), "+f"(d[11]), "+f"(d[12]), "+f"(d[13]), "+f"(d[14]), "+f"(d[15]),
        "+f"(d[16]), "+f"(d[17]), "+f"(d[18]), "+f"(d[19]), "+f"(d[20]), "+f"(d[21]), "+f"(d[22]), "+f"(d[23]),
        "+f"(d[24]), "+f"(d[25]), "+f"(d[26]), "+f"(d[27]), "+f"(d[28]), "+f"(d[29]), "+f"(d[30]), "+f"(d[31]),
        "+f"(d[32]), "+f"(d[33]), "+f"(d[34]), "+f"(d[35]), "+f"(d[36]), "+f"(d[37]), "+f"(d[38]), "+f"(d[39])
      : "r"(da), "n"(HA), "r"(db), "n"(HB), "r"(sc));
  }
};
template <> struct WgSST<192> {
  template <uint32_t HA, uint32_t HB>
  static __device__ __forceinline__ void mma(float* d, uint32_t da, uint32_t db, int sc) {
    asm volatile("{\n.reg .pred p;\n.reg .b64 da, db;\nsetp.ne.b32 p, %100, 0;\n"
      "mov.b64 da, {%96, %97};\nmov.b64 db, {%98, %99};\n"
      "wgmma.mma_async.sync.aligned.m64n192k16.f32.bf16.bf16 {"
      "%0, %1, %2, %3, %4, %5, %6, %7, %8, %9, %10, %11, %12, %13, %14, %15, "
      "%16, %17, %18, %19, %20, %21, %22, %23, %24, %25, %26, %27, %28, %29, %30, %31, "
      "%32, %33, %34, %35, %36, %37, %38, %39, %40, %41, %42, %43, %44, %45, %46, %47, "
      "%48, %49, %50, %51, %52, %53, %54, %55, %56, %57, %58, %59, %60, %61, %62, %63, "
      "%64, %65, %66, %67, %68, %69, %70, %71, %72, %73, %74, %75, %76, %77, %78, %79, "
      "%80, %81, %82, %83, %84, %85, %86, %87, %88, %89, %90, %91, %92, %93, %94, %95"
      "}, da, db, p, 1, 1, 0, 1;\n}\n"
      : "+f"(d[0]), "+f"(d[1]), "+f"(d[2]), "+f"(d[3]), "+f"(d[4]), "+f"(d[5]), "+f"(d[6]), "+f"(d[7]),
        "+f"(d[8]), "+f"(d[9]), "+f"(d[10]), "+f"(d[11]), "+f"(d[12]), "+f"(d[13]), "+f"(d[14]), "+f"(d[15]),
        "+f"(d[16]), "+f"(d[17]), "+f"(d[18]), "+f"(d[19]), "+f"(d[20]), "+f"(d[21]), "+f"(d[22]), "+f"(d[23]),
        "+f"(d[24]), "+f"(d[25]), "+f"(d[26]), "+f"(d[27]), "+f"(d[28]), "+f"(d[29]), "+f"(d[30]), "+f"(d[31]),
        "+f"(d[32]), "+f"(d[33]), "+f"(d[34]), "+f"(d[35]), "+f"(d[36]), "+f"(d[37]), "+f"(d[38]), "+f"(d[39]),
        "+f"(d[40]), "+f"(d[41]), "+f"(d[42]), "+f"(d[43]), "+f"(d[44]), "+f"(d[45]), "+f"(d[46]), "+f"(d[47]),
        "+f"(d[48]), "+f"(d[49]), "+f"(d[50]), "+f"(d[51]), "+f"(d[52]), "+f"(d[53]), "+f"(d[54]), "+f"(d[55]),
        "+f"(d[56]), "+f"(d[57]), "+f"(d[58]), "+f"(d[59]), "+f"(d[60]), "+f"(d[61]), "+f"(d[62]), "+f"(d[63]),
        "+f"(d[64]), "+f"(d[65]), "+f"(d[66]), "+f"(d[67]), "+f"(d[68]), "+f"(d[69]), "+f"(d[70]), "+f"(d[71]),
        "+f"(d[72]), "+f"(d[73]), "+f"(d[74]), "+f"(d[75]), "+f"(d[76]), "+f"(d[77]), "+f"(d[78]), "+f"(d[79]),
        "+f"(d[80]), "+f"(d[81]), "+f"(d[82]), "+f"(d[83]), "+f"(d[84]), "+f"(d[85]), "+f"(d[86]), "+f"(d[87]),
        "+f"(d[88]), "+f"(d[89]), "+f"(d[90]), "+f"(d[91]), "+f"(d[92]), "+f"(d[93]), "+f"(d[94]), "+f"(d[95])
      : "r"(da), "n"(HA), "r"(db), "n"(HB), "r"(sc));
  }
};

struct FftConst {
  uint32_t f[2][4], fi[4][4];
  float ta[4], tb[4];
};
__device__ __forceinline__ void cis(int m, float scale, float& c, float& s) {
  const float a = (float)m * (-6.283185307179586f * scale);
  c = __cosf(a);
  s = __sinf(a);
}
__device__ __forceinline__ void fft_tables(uint32_t (&v)[12], int tw) {
  const int row = tw >> 2, ch = tw & 3;
#pragma unroll
  for (int i = 0; i < 4; i++) {
    float c[2], s[2], x[2];
#pragma unroll
    for (int e = 0; e < 2; e++) {
      cis((((32 * (8 * ch + 2 * i + e) + 15) * (4 * row - 63) + 2048) & 4095) - 2048, 1.f / 4096, c[e], s[e]);
      float gc, gs;
      cis((((row & 15) * (8 * (ch & 1) + 2 * i + e) + 8) & 15) - 8, 1.f / 16, gc, gs);
      x[e] = (row >> 4) == (ch >> 1) ? gc : (ch >> 1) ? gs : -gs;
    }
    v[i] = pack2(c[0] * 0.125f, c[1] * 0.125f);
    v[4 + i] = pack2(s[0] * 0.125f, s[1] * 0.125f);
    v[8 + i] = pack2(x[0], x[1]);
  }
#pragma unroll
  for (int i = 0; i < 12; i++) asm volatile("" : "+r"(v[i]));
}
__device__ __forceinline__ void fft_tables_store(const uint32_t (&v)[12], uint32_t sb, int tw) {
  const int row = tw >> 2;
  const uint32_t x = ((tw ^ (row >> 1)) & 3) << 4, a = sb + OFF_FT + (16 * (row >> 3) + (row & 7)) * 64 + x;
  sts128(a, v[0], v[1], v[2], v[3]);
  sts128(a + 512, v[4], v[5], v[6], v[7]);
  sts128(sb + OFF_GT + row * 64 + x, v[8], v[9], v[10], v[11]);
}
__device__ __forceinline__ void fft_twiddles(float (&v)[4], int tw) {
#pragma unroll
  for (int i = 0; i < 2; i++) {
    float c, s;
    cis((2 * (2 * (tw & 3) + i) - 15) * (4 * (tw >> 2) - 63), 1.f / 4096, c, s);
    v[2 * i] = __fdividef(-s, 1.f + c);
    v[2 * i + 1] = s;
  }
  pin<4>(v);
}
__device__ __forceinline__ void fft_matrices(FftConst& k, uint32_t sb, int w, int lane) {
  const uint32_t x = (lane >> 1) & 3;
  const uint4 t0 = lds128(sb + OFF_TT + 512 * w + 16 * lane), t1 = lds128(sb + OFF_TT + 512 * w + 16 * (lane ^ 3));
  k.ta[0] = __uint_as_float(t0.x); k.tb[0] = __uint_as_float(t0.y); k.ta[1] = __uint_as_float(t0.z); k.tb[1] = __uint_as_float(t0.w);
  k.ta[3] = __uint_as_float(t1.x); k.tb[3] = __uint_as_float(t1.y); k.ta[2] = __uint_as_float(t1.z); k.tb[2] = __uint_as_float(t1.w);
#pragma unroll
  for (int i = 0; i < 2; i++) {
    ldsm4(k.f[i], sb + OFF_FT + (16 * w + (lane & 15)) * 64 + (((2 * i + (lane >> 4)) ^ x) << 4));
    ldsm4t(k.fi[i], sb + OFF_FT + (32 * i + lane) * 64 + ((w ^ x) << 4));
#pragma unroll
    for (int j = 0; j < 4; j++) {
      k.fi[2 + i][j] = (j & 1) ? k.fi[i][j - 1] ^ 0x80008000u : k.fi[i][j + 1];
      asm volatile("" : "+r"(k.fi[2 + i][j]));
    }
  }
}
__device__ __forceinline__ void rot(bool inv, float& x, float& y, float a, float b) {
  x = fmaf(inv ? -a : a, y, x);
  y = fmaf(inv ? -b : b, x, y);
  x = fmaf(inv ? -a : a, y, x);
}
__device__ __forceinline__ void twiddle_fwd(uint32_t (&a)[4][4], float* d, const FftConst& k) {
#pragma unroll
  for (int q = 0; q < 4; q++)
#pragma unroll
    for (int j = 0; j < 2; j++) {
      float* x = d + 8 * q + 4 * j;
      rot(j, x[0], x[2], k.ta[2 * j], k.tb[2 * j]);
      rot(j, x[1], x[3], k.ta[2 * j + 1], k.tb[2 * j + 1]);
      a[q & 2][2 * j + (q & 1)] = pack2(x[0], x[1]);
      a[(q & 2) + 1][2 * j + (q & 1)] = pack2(x[2], x[3]);
    }
}
__device__ __forceinline__ void g_step(float* d, const uint32_t (&a)[4][4], uint32_t dre, uint32_t dim) {
  WgRS<32>::set<HI_SW64>(d, a[0], dre);
  WgRS<32>::set<HI_SW64>(d + 16, a[2], dre);
  WgRS<32>::mma<HI_SW64>(d, a[1], dim);
  WgRS<32>::mma<HI_SW64>(d + 16, a[3], dim);
  wg_commit();
}

__device__ __forceinline__ void conv_channel(const FftConst& k, uint32_t sb, int c, int wg, int w, int lane) {
  const uint32_t cb = sb + off_ch(c), bars = sb + OFF_BAR;
  const uint32_t du = desc_lo(cb, 1024), dg = desc_lo(sb + OFF_GT, 16), dz = desc_lo(cb + U_BYTES, 16);
  float U[32], H[32];
  uint32_t a[4][4], e[4][4];
  const float dv = __uint_as_float(lds32(sb + OFF_D + 4 * c));
  wg_fence();
  WgRS<64>::set<HI_SW32>(H, k.f[0], du + 256);
  WgRS<64>::mma<HI_SW32>(H, k.f[1], du + 256 + 32);
  wg_commit();
  wg_wait<0>();
  pin<32>(H);
  twiddle_fwd(a, H, k);
  if (ATT_GATE && H_EARLY) mbar_wait(bars + 8 * B_ATTN, 0);
  mbar_wait(bars + 8 * (B_U + (c < 3 ? c : 3)), 0);
  TSM(w == 0 && c < 3, 7 + wg);
  wg_fence();
  WgRS<64>::set<HI_SW32>(U, k.f[0], du);
  WgRS<64>::mma<HI_SW32>(U, k.f[1], du + 32);
  wg_commit();
  g_step(H, a, dg, dg + 64);
  wg_wait<1>();
  pin<32>(U);
  twiddle_fwd(e, U, k);
  wg_fence();
  g_step(U, e, dg, dg + 64);
  wg_wait<0>();
  pin<32>(U);
  pin<32>(H);
#pragma unroll
  for (int j = 0; j < 2; j++) {
    float pr[4][2], pi[4][2];
#pragma unroll
    for (int x = 0; x < 2; x++) {
      H[4 * j + x] += dv;
#pragma unroll
      for (int m = 0; m < 4; m++) {
#pragma unroll
        for (int q = 0; q <= m; q++) {
          const int ih = 16 * (q >> 1) + 2 * (q & 1) + 4 * j + x, iu = 16 * ((m - q) >> 1) + 2 * ((m - q) & 1) + 4 * j + x;
          pr[m][x] = q ? fmaf(H[ih], U[iu], pr[m][x]) : H[ih] * U[iu];
          pi[m][x] = q ? fmaf(H[ih], U[iu + 8], pi[m][x]) : H[ih] * U[iu + 8];
          pr[m][x] = fmaf(-H[ih + 8], U[iu + 8], pr[m][x]);
          pi[m][x] = fmaf(H[ih + 8], U[iu], pi[m][x]);
        }
      }
    }
#pragma unroll
    for (int m = 0; m < 4; m++) {
      a[m & 2][2 * j + (m & 1)] = pack2(pr[m][0], pr[m][1]);
      a[(m & 2) + 1][2 * j + (m & 1)] = pack2(pi[m][0], pi[m][1]);
    }
  }
  wg_fence();
  g_step(U, a, dg + 64, dg);
  const uint32_t za = cb + U_BYTES + (8 * w + (lane & 7)) * 128 + (((lane >> 3) ^ (lane & 7)) << 4);
  const uint32_t ya = cb + (lane >> 4) * 1024 + (8 * w + (lane & 7)) * 32 + ((((lane >> 3) ^ (lane >> 2)) & 1) << 4);
  wg_sync(1 + wg);
  wg_wait<0>();
  pin<32>(U);
  TSIF(w == 0, 80 + c);
#pragma unroll
  for (int p = 0; p < 2; p++) {
#pragma unroll
    for (int i = 0; i < 4; i++) {
      const int j = i & 1;
      float* x = U + 16 * p + 4 * j + (i & 2);
      rot(!j, x[8], x[0], k.ta[2 * j], k.tb[2 * j]);
      rot(!j, x[9], x[1], k.ta[2 * j + 1], k.tb[2 * j + 1]);
      e[p][i] = pack2(x[8], x[9]);
      e[2 + p][i] = pack2(x[0], x[1]);
    }
    stsm4(za ^ (64 * p), e[p]);
    stsm4((za ^ (64 * p)) + 4096, e[2 + p]);
  }
  fence_async_smem();
  wg_sync(1 + wg);
  wg_fence();
  WgRS<64>::set<HI_SW128>(H, k.fi[0], dz);
#pragma unroll
  for (int ks = 1; ks < 4; ks++) WgRS<64>::mma<HI_SW128>(H, k.fi[ks], dz + 128 * ks);
  wg_commit();
  wg_wait<0>();
  pin<32>(H);
  TSIF(w == 0, 88 + c);
#pragma unroll
  for (int j = 0; j < 8; j++)
    a[j >> 2][j & 3] = j < 2 ? pack2(H[4 * j], H[4 * j + 1]) : pack2(H[4 * j] + H[4 * j - 6], H[4 * j + 1] + H[4 * j - 5]);
  stsm4(ya, a[0]);
  stsm4(ya + 2048, a[1]);
  fence_async_smem();
  __syncwarp();
}

__device__ __forceinline__ void prep_slab(uint4* res, const uint2* sw, uint32_t sb, int slab, int w, int lane) {
  const int t = lane & 3, tp = (lane & 7) >> 1, pos = 8 * tp + 2 * (((lane >> 3) + tp) & 3) + (lane & 1);
  const uint32_t base = sb + OFF_KVS + slab * KVS_BYTES + pos * 128;
  uint32_t kk[2][4][4], vv[2][4];
  mbar_wait(sb + OFF_BAR + 8 * (B_KV + slab), 0);
#pragma unroll
  for (int h = 0; h < 2; h++) {
#pragma unroll
    for (int j = 0; j < 4; j++) {
      const uint32_t a = base + 128 * j;
      ldsm4t(kk[h][j], a + (((w + 4 * h) ^ ((a >> 7) & 7)) << 4));
    }
    const uint32_t a = base + KVS_V;
    ldsm4t(vv[h], a + (((w + 4 * h) ^ ((a >> 7) & 7)) << 4));
  }
#pragma unroll
  for (int h = 0; h < 2; h++) {
    uint32_t (&k)[4][4] = kk[h];
    uint32_t (&v)[4] = vv[h];
    const uint32_t w0 = __byte_perm(sw[h].x, 0, 0x1010), w1 = __byte_perm(sw[h].x, 0, 0x3232);
    const uint32_t w2 = __byte_perm(sw[h].y, 0, 0x1010), w3 = __byte_perm(sw[h].y, 0, 0x3232);
#pragma unroll
    for (int m = 0; m < 4; m++)
      v[m] = bmul(badd(badd(badd(bmul(k[0][m], w3), bmul(k[1][m], w2)), bmul(k[2][m], w1)), bmul(k[3][m], w0)), v[m]);
    uint32_t a[4];
#pragma unroll
    for (int m = 0; m < 4; m++) a[m] = (t & 1) ? v[(m + 3) & 3] : v[m];
    res[h] = (t & 2) ? make_uint4(a[2], a[3], a[0], a[1]) : make_uint4(a[0], a[1], a[2], a[3]);
  }
}

__device__ __forceinline__ void prep_gate(const Params& p, int b, int w, int lane) {
  uint2 gw[5], x[4][5];
#pragma unroll
  for (int j = 0; j < 5; j++) gw[j] = ldg64(reinterpret_cast<const uint2*>(p.gate_w) + lane + 32 * j);
#pragma unroll
  for (int i = 0; i < 4; i++)
#pragma unroll
    for (int j = 0; j < 5; j++)
      x[i][j] = ldg64(reinterpret_cast<const uint2*>(p.q) + (16 * b + 4 * w + i) * (DIM / 4) + lane + 32 * j);
  float s[4];
#pragma unroll
  for (int i = 0; i < 4; i++) {
    s[i] = 0.f;
#pragma unroll
    for (int j = 0; j < 5; j++) {
      const uint32_t m0 = bmul(x[i][j].x, gw[j].x), m1 = bmul(x[i][j].y, gw[j].y);
      s[i] += (bf_lo(m0) + bf_hi(m0)) + (bf_lo(m1) + bf_hi(m1));
    }
  }
  const bool h = lane & 16, q = lane & 8;
  const float a = (h ? s[2] : s[0]) + __shfl_xor_sync(0xffffffffu, h ? s[0] : s[2], 16);
  const float c = (h ? s[3] : s[1]) + __shfl_xor_sync(0xffffffffu, h ? s[1] : s[3], 16);
  float z = (q ? c : a) + __shfl_xor_sync(0xffffffffu, q ? a : c, 8);
#pragma unroll
  for (int o = 4; o > 0; o >>= 1) z += __shfl_xor_sync(0xffffffffu, z, o);
  z = bf_lo(pack2(z, 0.f));
  if ((lane & 7) == 0) g_gate[16 * b + 4 * w + (lane >> 3)] = bf_lo(pack2(__fdividef(1.f, 1.f + __expf(-z)), 0.f));
}

__device__ __forceinline__ uint32_t bmax(uint32_t a, uint32_t b) {
  uint32_t d;
  asm("max.bf16x2 %0, %1, %2;" : "=r"(d) : "r"(a), "r"(b));
  return d;
}
__device__ __forceinline__ void softmax_two(const float (&l)[2][2], uint32_t& p0, uint32_t& p1) {
  constexpr float kScale = 0.22360679774997896f, kLog2e = 1.4426950408889634f;
  const uint32_t r0 = pack2(l[0][0], l[1][0]), r1 = pack2(l[0][1], l[1][1]);
  const uint32_t x0 = pack2(bf_lo(r0) * kScale, bf_hi(r0) * kScale), x1 = pack2(bf_lo(r1) * kScale, bf_hi(r1) * kScale);
  uint32_t m = bmax(x0, x1);
  m = bmax(m, __shfl_xor_sync(0xffffffffu, m, 1));
  m = bmax(m, __shfl_xor_sync(0xffffffffu, m, 2));
  const float m0 = bf_lo(m) * kLog2e, m1 = bf_hi(m) * kLog2e;
  p0 = pack2(ex2(bf_lo(x0) * kLog2e - m0), ex2(bf_lo(x1) * kLog2e - m0));
  p1 = pack2(ex2(bf_hi(x0) * kLog2e - m1), ex2(bf_hi(x1) * kLog2e - m1));
}

__device__ __forceinline__ void halo_read(uint32_t (&kpv)[10], uint32_t (&vpv)[10], uint32_t (&tg)[7], const uint4* hp) {
#pragma unroll
  for (int j = 0; j < 7; j++) {
    uint32_t x0, x1, x2;
    asm volatile("ld.relaxed.gpu.global.v4.u32 {%0, %1, %2, %3}, [%4];"
                 : "=r"(x0), "=r"(x1), "=r"(x2), "=r"(tg[j]) : "l"(hp + 32 * j) : "memory");
    if (j < 4) kpv[3 * j] = x0; else vpv[3 * j - 10] = x0;
    if (j < 3) kpv[3 * j + 1] = x1; else vpv[3 * j - 9] = x1;
    if (j < 3) kpv[3 * j + 2] = x2; else if (j < 6) vpv[3 * j - 8] = x2;
  }
}

template <int ROT>
__device__ __forceinline__ void pack_qkv(const float* acc, uint32_t (&qlo)[10], uint32_t (&qhi)[10], uint32_t (&klo)[10],
                                         uint32_t (&khi)[10], uint32_t (&vlo)[10], uint32_t (&vhi)[10]) {
#pragma unroll
  for (int j = 0; j < 10; j++) {
    const int x = (j + ROT) % 10, tq = x < 8 ? x : 16 + x, tk = x < 8 ? 8 + x : 18 + x, tv = x < 8 ? 16 + x : 20 + x;
    khi[j] = pack2(acc[4 * tk + 2], acc[4 * tk + 3]);
    vhi[j] = movm(pack2(acc[4 * tv + 2], acc[4 * tv + 3]));
    qlo[j] = pack2(acc[4 * tq], acc[4 * tq + 1]);
    qhi[j] = pack2(acc[4 * tq + 2], acc[4 * tq + 3]);
    klo[j] = pack2(acc[4 * tk], acc[4 * tk + 1]);
    vlo[j] = pack2(acc[4 * tv], acc[4 * tv + 1]);
    asm volatile("" : "+r"(khi[j]), "+r"(qlo[j]), "+r"(qhi[j]), "+r"(klo[j]), "+r"(vlo[j]));
  }
}

template <int ROT> __device__ __forceinline__ void halo_send(const float* acc, uint4* ho, uint32_t tag) {
#pragma unroll
  for (int j = 0; j < 7; j++) {
    uint32_t x[3];
#pragma unroll
    for (int e = 0; e < 3; e++) {
      const int i = 3 * j + e, y = (i % 10 + ROT) % 10, tk = y < 8 ? 8 + y : 18 + y, tv = y < 8 ? 16 + y : 20 + y;
      x[e] = i < 10 ? pack2(acc[4 * tk + 2], acc[4 * tk + 3]) : i < 20 ? movm(pack2(acc[4 * tv + 2], acc[4 * tv + 3])) : 0u;
    }
    asm volatile("st.relaxed.gpu.global.v4.u32 [%0], {%1, %2, %3, %4};" ::"l"(ho + 32 * j), "r"(x[0]), "r"(x[1]), "r"(x[2]), "r"(tag) : "memory");
  }
}

__device__ __forceinline__ void attention(float* acc, uint32_t sb, int b, int par, int w, int lane, uint32_t tag) {
  const int g = lane >> 2, t = lane & 3;
  uint32_t klo[10], khi[10], vlo[10], vhi[10], qlo[10], qhi[10], kpv[10], vpv[10];
  if (HALO_FIRST && w == 3 && b < NCTA - 8) {
    uint4* ho = g_halo + (b * 2 + par) * 224 + lane;
    if (tail_first(b & 7)) halo_send<8>(acc, ho, tag);
    else halo_send<0>(acc, ho, tag);
    TSIF(par == 0, 76);
    pin<120>(acc);
  }
  if (tail_first(b & 7)) pack_qkv<8>(acc, qlo, qhi, klo, khi, vlo, vhi);
  else pack_qkv<0>(acc, qlo, qhi, klo, khi, vlo, vhi);
  const uint32_t xa = sb + OFF_KVX + (par * 3) * 2560 + lane * 16;
  if (w < 3) {
    sts128(xa + w * 2560, khi[0], khi[1], khi[2], khi[3]);
    sts128(xa + w * 2560 + 512, khi[4], khi[5], khi[6], khi[7]);
    sts128(xa + w * 2560 + 1024, khi[8], khi[9], vhi[0], vhi[1]);
    sts128(xa + w * 2560 + 1536, vhi[2], vhi[3], vhi[4], vhi[5]);
    sts128(xa + w * 2560 + 2048, vhi[6], vhi[7], vhi[8], vhi[9]);
  } else if (!HALO_FIRST && b < NCTA - 8) {
    uint4* ho = g_halo + (b * 2 + par) * 224 + lane;
#pragma unroll
    for (int j = 0; j < 7; j++) {
      const uint32_t x0 = j < 4 ? khi[3 * j] : vhi[3 * j - 10], x1 = j < 3 ? khi[3 * j + 1] : vhi[3 * j - 9];
      const uint32_t x2 = j < 3 ? khi[3 * j + 2] : j < 6 ? vhi[3 * j - 8] : 0u;
      asm volatile("st.relaxed.gpu.global.v4.u32 [%0], {%1, %2, %3, %4};" ::"l"(ho + 32 * j), "r"(x0), "r"(x1), "r"(x2), "r"(tag) : "memory");
    }
  }
  TSIF(par == 0 && w == 1, 64);
  TSIF(par == 0 && w == 3 && !HALO_FIRST, 76);
#pragma unroll
  for (int j = 0; j < 10; j++) vlo[j] = movm(vlo[j]);
  const bool far0 = 2 * t > g, far1 = 2 * t + 1 > g;
  const uint32_t mfar = (far0 ? 0x0000FFFFu : 0u) | (far1 ? 0xFFFF0000u : 0u);
  float slo[4][2], shi[4][2], lg[2][2];
  uint32_t phi[4], plo[4], qml[4], qmh[4];
#pragma unroll
  for (int h = 0; h < 4; h++) {
    const int f = h == 0 ? 0 : h == 1 ? 3 : h == 2 ? 5 : 8, hf = h < 2 ? 2 : 7;
    const bool mine = (h & 1) ? t >= 2 : t < 2;
    qml[h] = mine ? qlo[hf] : 0u;
    qmh[h] = mine ? qhi[hf] : 0u;
    float a[4] = {0.f, 0.f, 0.f, 0.f}, c[4] = {0.f, 0.f, 0.f, 0.f};
    mma16816(a, qlo[f], qhi[f], qlo[f + 1], qhi[f + 1], klo[f], klo[f + 1]);
    mma16816(c, qlo[f], qhi[f], qlo[f + 1], qhi[f + 1], khi[f], khi[f + 1]);
    mma1688(a, qml[h], qmh[h], klo[hf]);
    mma1688(c, qml[h], qmh[h], khi[hf]);
    slo[h][0] = a[0];
    slo[h][1] = a[1];
    shi[h][0] = lg[h & 1][0] = far0 ? a[2] : c[2];
    shi[h][1] = lg[h & 1][1] = far1 ? a[3] : c[3];
    if (!ATT_MERGE && (h & 1)) softmax_two(lg, phi[h - 1], phi[h]);
  }
  TSIF(par == 0 && w == 1, 65);
  wg_sync(1 + par);
  TSIF(par == 0 && w == 1, 66);
  const bool nohist = (w == 0) && (b < 8);
  const uint4* hp = g_halo + ((b - 8) * 2 + par) * 224 + lane;
  uint32_t tg[7];
  if (w > 0) {
    const uint4 v0 = lds128(xa + (w - 1) * 2560), v1 = lds128(xa + (w - 1) * 2560 + 512), v2 = lds128(xa + (w - 1) * 2560 + 1024);
    const uint4 v3 = lds128(xa + (w - 1) * 2560 + 1536), v4 = lds128(xa + (w - 1) * 2560 + 2048);
    kpv[0] = v0.x; kpv[1] = v0.y; kpv[2] = v0.z; kpv[3] = v0.w; kpv[4] = v1.x; kpv[5] = v1.y; kpv[6] = v1.z; kpv[7] = v1.w;
    kpv[8] = v2.x; kpv[9] = v2.y; vpv[0] = v2.z; vpv[1] = v2.w; vpv[2] = v3.x; vpv[3] = v3.y; vpv[4] = v3.z; vpv[5] = v3.w;
    vpv[6] = v4.x; vpv[7] = v4.y; vpv[8] = v4.z; vpv[9] = v4.w;
  } else if (nohist) {
#pragma unroll
    for (int j = 0; j < 10; j++) kpv[j] = vpv[j] = 0u;
  } else {
    TSIF(par == 0, 77);
    halo_read(kpv, vpv, tg, hp);
  }
  if (w == 0 && !nohist) {
    int spins = 0;
    while (true) {
      bool ok = true;
#pragma unroll
      for (int j = 0; j < 7; j++) ok = ok && tg[j] == tag;
      if (__all_sync(0xffffffffu, ok) || ++spins > SPIN_LIMIT) break;
      halo_read(kpv, vpv, tg, hp);
    }
    TSIF(par == 0, 79);
  }
#pragma unroll
  for (int h = 0; h < 4; h++) {
    const int f = h == 0 ? 0 : h == 1 ? 3 : h == 2 ? 5 : 8, hf = h < 2 ? 2 : 7;
    float a[4] = {0.f, 0.f, 0.f, 0.f};
    mma16816(a, qlo[f], qhi[f], qlo[f + 1], qhi[f + 1], kpv[f], kpv[f + 1]);
    mma1688(a, qml[h], qmh[h], kpv[hf]);
    const float ninf = __int_as_float(0xff800000);
    lg[h & 1][0] = far0 ? (nohist ? ninf : a[0]) : slo[h][0];
    lg[h & 1][1] = far1 ? (nohist ? ninf : a[1]) : slo[h][1];
    if (h & 1) {
      softmax_two(lg, plo[h - 1], plo[h]);
      if (ATT_MERGE) {
        const float lh[2][2] = {{shi[h - 1][0], shi[h - 1][1]}, {shi[h][0], shi[h][1]}};
        softmax_two(lh, phi[h - 1], phi[h]);
      }
    }
  }
  TSIF(par == 0 && w <= 1, 67 + w);
  uint32_t ov[20];
#pragma unroll
  for (int hp = 0; hp < 2; hp++) {
    const int hf = hp ? 7 : 2;
    float sh[4] = {0.f, 0.f, 0.f, 0.f}, i0 = 0.f, i1 = 0.f;
#pragma unroll
    for (int e = 0; e < 2; e++) {
      const int h = 2 * hp + e, f = h == 0 ? 0 : h == 1 ? 3 : h == 2 ? 5 : 8;
      const uint32_t a0 = plo[h] & mfar, a2 = plo[h] & ~mfar, a3 = phi[h] & mfar, c1 = phi[h] & ~mfar;
      float sum[4] = {0.f, 0.f, 0.f, 0.f};
      mma1688(sum, plo[h], phi[h], 0x3F803F80u);
      const float r0 = rcp(sum[0]), r1 = rcp(sum[2]);
#pragma unroll
      for (int j = f; j < f + 2; j++) {
        float o[4] = {0.f, 0.f, 0.f, 0.f};
        mma16816(o, a0, 0u, a2, a3, vpv[j], vlo[j]);
        mma1688(o, 0u, c1, vhi[j]);
        ov[2 * j] = pack2(o[0] * r0, o[1] * r0);
        ov[2 * j + 1] = pack2(o[2] * r1, o[3] * r1);
      }
      const bool mine = e ? g >= 4 : g < 4;
      mma16816(sh, a0, 0u, a2, a3, mine ? vpv[hf] : 0u, mine ? vlo[hf] : 0u);
      mma1688(sh, 0u, c1, mine ? vhi[hf] : 0u);
      if (e == 0 || t >= 2) {
        i0 = r0;
        i1 = r1;
      }
    }
    ov[2 * hf] = pack2(sh[0] * i0, sh[1] * i0);
    ov[2 * hf + 1] = pack2(sh[2] * i1, sh[3] * i1);
  }
  TS(32 + 4 * par + w);
  mbar_wait(sb + OFF_BAR + 8 * B_P1, 0);
  const uint32_t oa = sb + OFF_OA + (lane >> 4) * 2048 + (32 * w + 2 * (lane & 15) + par) * 16;
#pragma unroll
  for (int j = 0; j < 5; j++) stsm4(oa + 4096 * j, ov + 4 * j);
  TSIF(par == 0 && w == 0, 120);
  fence_async_smem();
  TSIF(par == 0 && w == 0, 121);
  __syncwarp();
  if (lane == 0) mbar_arrive(sb + OFF_BAR + 8 * B_ATTN);
  TSM(w == 0 || w == 2, 122 + par + (w == 2 ? 3 : 0));
}

struct Maps {
  CUtensorMap x, wm, wt, k, v, y, wo, qm, qt, om, ot, u;
};

__device__ __forceinline__ void load_stage(uint32_t sb, int kb, int b, const Maps& m) {
  const uint32_t st = sb + (kb & 3) * STAGE_BYTES, bar = sb + OFF_BAR + 8 * (B_FULL1 + (kb & 3));
  const int r = b >> 3, hg = b & 7, slab = kb - KV_KB;
  const bool kv = slab >= 0 && slab < 5;
  const uint32_t kbar = sb + OFF_BAR + 8 * (B_KV + slab), dst = sb + OFF_KVS + slab * KVS_BYTES;
  mbar_expect_tx(bar, STAGE_BYTES);
  if (kv) mbar_expect_tx(kbar, KVS_BYTES);
  tma_3d(st, &m.x, 64 * kb, 64 * r, 0, bar);
  if (kv && KV_MIX) tma_3d(dst, &m.k, 0, 32 * (b >> 1) - 3, 2 * slab + (b & 1), kbar);
  tma_3d(st + ST_W, &m.wm, 80 * hg + (tail_first(hg) ? 16 : 0), 64 * kb, 0, bar);
  if (kv && KV_MIX) tma_3d(dst + KVS_V, &m.v, 0, 32 * (b >> 1), 2 * slab + (b & 1), kbar);
  tma_3d(st + ST_WT, &m.wt, 80 * hg + (tail_first(hg) ? 0 : 64), 64 * kb, 0, bar);
  if (kv && !KV_MIX) tma_3d(dst, &m.k, 0, 32 * (b >> 1) - 3, 2 * slab + (b & 1), kbar);
  if (kv && !KV_MIX) tma_3d(dst + KVS_V, &m.v, 0, 32 * (b >> 1), 2 * slab + (b & 1), kbar);
}

__global__ void __launch_bounds__(NTHR, 1) fused_kernel(const __grid_constant__ Maps m, const Params p) {
  extern __shared__ __align__(1024) uint8_t smem[];
  const uint32_t sb = (uint32_t)__cvta_generic_to_shared(smem);
  const uint32_t bars = sb + OFF_BAR;
  const int tid = threadIdx.x, lane = tid & 31;
  int b = blockIdx.x;
  if (BMAP == 1) b = (((b & 63) >> 3) * 2 + (b & 1)) * 8 + (((b < 64 ? 0x6521 : 0x7430) >> (4 * ((b >> 1) & 3))) & 7);
  if (BMAP == 2) b = ((b & 63) >> 2) * 8 + (((b < 64 ? 0x6521 : 0x7430) >> (4 * (b & 3))) & 7);
  if (BMAP == 3) b = (((b & 63) >> 3) * 2 + (b & 1)) * 8 + (((b < 64 ? 0x7430 : 0x6521) >> (4 * ((b >> 1) & 3))) & 7);
  if (BMAP == 4) b = (((b >> 4) * 2 + (b & 1)) * 8) + ((b >> 1) & 7);
  if (BMAP == 5) b = 127 - b;
  const int r = b >> 3, hg = b & 7;

  if (tid == T_ISSUE) {
    TSM(true, 0);
#pragma unroll
    for (int i = 0; i < 4; i++) mbar_init(bars + 8 * (B_FULL1 + i), 1);
#pragma unroll
    for (int i = 0; i < 3; i++) mbar_init(bars + 8 * (B_KV + i), 1);
    fence_async_smem();
#pragma unroll 1
    for (int kb = 0; kb <= PRE2; kb++) load_stage(sb, kb, b, m);
  } else if (tid >= T_PF && tid < T_PF + 12) {
    tm_prefetch(&m.x + (tid - T_PF));
  } else if (tid == T_INIT) {
#pragma unroll
    for (int i = 0; i < 4; i++) mbar_init(bars + 8 * (B_EMPTY1 + i), 8);
#pragma unroll
    for (int i = 0; i < 8; i++) mbar_init(bars + 8 * (B_FULL2 + i), 1);
#pragma unroll
    for (int i = 0; i < 4; i++) mbar_init(bars + 8 * (B_EMPTY2 + i), 8);
#pragma unroll
    for (int i = 0; i < 4; i++) mbar_init(bars + 8 * (B_U + i), 1);
    mbar_init(bars + 8 * B_HA, 4);
    mbar_init(bars + 8 * B_GATE, 4);
    mbar_init(bars + 8 * B_HB, 1);
    mbar_init(bars + 8 * B_KVD, 4);
    mbar_init(bars + 8 * B_QF, 1);
    mbar_init(bars + 8 * B_ATTN, 8);
    mbar_init(bars + 8 * B_P1, 8);
    mbar_init(bars + 8 * B_C34, 1);
#pragma unroll
    for (int i = 0; i < 5; i++) mbar_init(bars + 8 * (B_YST + i), 4);
#pragma unroll
    for (int i = 0; i < 5; i++) mbar_init(bars + 8 * (B_US + i), 4);
    mbar_init(bars + 8 * B_YSIG, 1);
    mbar_init(bars + 8 * B_YFULL, 1);
    mbar_init(bars + 8 * B_EPOCH, 1);
    mbar_init(bars + 8 * B_PREP, 4);
    mbar_init(bars + 8 * B_USIG, 1);
    mbar_init(bars + 8 * B_WST, 1);
#pragma unroll
    for (int i = 3; i < 5; i++) mbar_init(bars + 8 * (B_KV + i), 1);
    mbar_init(bars + 8 * B_E3, 8);
    mbar_init(bars + 8 * B_LAST, 1);
    mbar_init(bars + 8 * B_OSIG, 1);
    mbar_init(bars + 8 * B_WOP, 1);
    fence_async_smem();
  }
  const int warp = __shfl_sync(0xffffffffu, tid >> 5, 0), wg = warp >> 2, w = warp & 3;
  __syncthreads();

  if (wg == 3) {
    asm volatile("setmaxnreg.dec.sync.aligned.u32 56;");
    if (w == 0) {
      if (lane == 0) {
#pragma unroll 1
        for (int kb = 1 + PRE2; kb < 10; kb++) {
          if (kb >= 4) mbar_wait(bars + 8 * (kb == 7 ? B_E3 : B_EMPTY1 + (kb & 3)), (kb >> 3) & 1);
          TSIF(kb >= 4, 44 + kb);
          load_stage(sb, kb, b, m);
          TSIF(kb == 3, 60);
          if (kb == TRIG_KB) mbar_arrive(bars + 8 * B_LAST);
        }
        mbar_wait(bars + 8 * B_WOP, 0);
        mbar_wait(bars + 8 * WL_TRIG, 0);
        mbar_wait(bars + 8 * B_EPOCH, 0);
        flag_wait(g_cnt + C_W + 32 * hg, (lds32(sb + OFF_EPOCH) + 1) * 16);
        TS(30);
#pragma unroll 1
        for (int j = 0; j < 8; j++) {
          if (j >= 6) mbar_wait(bars + 8 * (B_EMPTY2 + j - 6), 0);
          if (j == 4) mbar_wait(bars + 8 * B_ATTN, 0);
          TSIF(j >= 6, 100 + j);
          if (RF_GATE && j == 6) mbar_wait(bars + 8 * B_YSIG, 0);
          mbar_expect_tx(bars + 8 * (B_FULL2 + j), j == 0 ? WO_BYTES : j == 5 ? O_BYTES + WO_BYTES + 512 : O_BYTES + WO_BYTES);
          bulk_load(sb + off_w(j), g_WO + (hg * 8 + step_src(hg, j)) * 800, WO_BYTES, bars + 8 * (B_FULL2 + j));
        }
        mbar_wait(bars + 8 * (B_EMPTY2 + 3), 0);
        mbar_expect_tx(bars + 8 * B_QF, O_BYTES);
        tma_2d(sb + OFF_QS, &m.qm, 80 * hg, 128 * r, bars + 8 * B_QF);
        tma_2d(sb + OFF_QT, &m.qt, 80 * hg + 64, 128 * r, bars + 8 * B_QF);
      }
    } else if (w == 1) {
      unsigned epoch = 0;
      if (lane == 0) {
        epoch = atomicAdd(g_cnt + C_LAUNCH, 1u) / NCTA;
        asm volatile("st.shared.u32 [%0], %1;" ::"r"(sb + OFF_EPOCH), "r"(epoch) : "memory");
        mbar_arrive(bars + 8 * B_EPOCH);
        mbar_wait(bars + 8 * B_KVD, 0);
        mbar_expect_tx(bars + 8 * B_HB, 5 * 4096);
#pragma unroll 1
        for (int c = 0; c < 5; c++) {
          if (c == 3) mbar_wait(bars + 8 * B_S3, 0);
          bulk_load(sb + off_ch(c) + U_BYTES, p.ssm_k + (5 * b + c) * SEQ, 4096, bars + 8 * B_HB);
        }
#pragma unroll
        for (int c = 0; c < 4; c++) mbar_expect_tx(bars + 8 * (B_U + c), c < 3 ? U_BYTES : 2 * U_BYTES);
        const uint4* usrc = g_U + 5 * b * U_PITCH;
        mbar_wait(bars + 8 * B_USIG, 0);
        flag_wait(g_cnt + C_PREP + 32 * (b & 15), (epoch + 1) * NCTA);
        TS(23);
#pragma unroll
        for (int c = 0; c < 5; c++) {
          if (c == 3) mbar_wait(bars + 8 * (B_U + 2), 0);
          bulk_load(sb + off_ch(c), usrc + c * U_PITCH, U_BYTES, bars + 8 * (B_U + (c < 3 ? c : 3)));
          TSIF(c == 0 || c == 4, 116 + (c >> 2));
        }
      }
      epoch = __shfl_sync(0xffffffffu, epoch, 0);
      if (lane < 8) {
        const int src = (b & ~7) | step_src(hg, lane);
        mbar_wait(bars + 8 * B_OSIG, 0);
        TS(20);
        flag_wait(g_cnt + C_O + 32 * src, epoch + 1);
        if (lane >= 1 && lane < 4) bulk_load(sb + off_o(lane), g_O + src * 1280, O_BYTES, bars + 8 * (B_FULL2 + lane));
        __syncwarp(0xff);
        TS(21);
        if (lane == 5) bulk_load(sb + OFF_GATE, g_gate + 128 * r, 512, bars + 8 * (B_FULL2 + 5));
#pragma unroll 1
        for (int j = 4; j < 8; j++) {
          if (lane == j) {
            mbar_wait(bars + 8 * (j < 6 ? B_C34 : B_EMPTY2 + j - 6), 0);
            if (RF_GATE && j == 6) mbar_wait(bars + 8 * B_YSIG, 0);
            bulk_load(sb + off_o(j), g_O + src * 1280, O_BYTES, bars + 8 * (B_FULL2 + j));
          }
          __syncwarp(0xff);
        }
        TS(22);
      }
    } else if (w == 2) {
      mbar_wait(bars + 8 * B_PREP, 0);
      flag_signal(g_cnt + C_PREP, 16, lane);
      TS(25);
      if (lane == 0) mbar_arrive(bars + 8 * B_USIG);
      mbar_wait(bars + 8 * B_GATE, 0);
      if ((NOMB & 1) && lane == 0) asm volatile("fence.release.gpu;" ::: "memory");
      mbar_wait(bars + 8 * B_ATTN, 0);
      if (lane == 0) {
        if (O_DEFER) mbar_wait(bars + 8 * (B_U + 3), 0);
        asm volatile("cp.async.bulk.global.shared::cta.bulk_group [%0], [%1], 20480;\ncp.async.bulk.commit_group;\n"
                     "cp.async.bulk.wait_group 0;\nfence.proxy.async.global;" ::"l"(g_O + b * 1280), "r"(sb + OFF_OA) : "memory");
      }
      TS(74);
      if (!(NOMB & 1)) flag_signal(g_cnt + C_O + 32 * b, 1, lane);
      else if (lane == 0) flag_bump(g_cnt + C_O + 32 * b);
      TS(26);
      if (lane == 0) mbar_arrive(bars + 8 * B_OSIG);

    } else {
      if (lane == 0) {
        uint4* dst = g_WO + (hg * 8 + (r >> 1)) * 800 + (r & 1) * 80;
        mbar_wait(bars + 8 * B_P1, 0);
        mbar_wait(bars + 8 * WB_TRIG, 0);
        mbar_expect_tx(bars + 8 * B_WST, WO_BYTES / 2);
        tma_3d(sb + OFF_WS, &m.wo, 0, 40 * r, 5 * hg, bars + 8 * B_WST);
        mbar_wait(bars + 8 * B_WST, 0);
        mbar_wait(bars + 8 * WO_TRIG, 0);
#pragma unroll 1
        for (int n = 0; n < 5; n++)
          asm volatile("cp.async.bulk.global.shared::cta.bulk_group [%0], [%1], 1280;" ::"l"(dst + 160 * n), "r"(sb + OFF_WS + 1280 * n) : "memory");
        asm volatile("cp.async.bulk.commit_group;\ncp.async.bulk.wait_group 0;\nfence.proxy.async.global;" ::: "memory");
        if (!(NOMB & 4)) asm volatile("fence.release.gpu;" ::: "memory");
        flag_bump(g_cnt + C_W + 32 * hg);
        mbar_arrive(bars + 8 * B_WOP);
        TS(71);
#pragma unroll 1
        for (int c = 0; c < 5; c++) {
          mbar_wait(bars + 8 * (B_YST + c), 0);
          asm volatile("cp.async.bulk.global.shared::cta.bulk_group [%0], [%1], 4096;\ncp.async.bulk.commit_group;"
                       ::"l"(g_Y + (5 * b + c) * Y_PITCH), "r"(sb + off_ch(c)) : "memory");
          if (c == 2) {
            asm volatile("cp.async.bulk.wait_group.read 0;" ::: "memory");
            mbar_arrive(bars + 8 * B_C34);
          }
        }
        asm volatile("cp.async.bulk.wait_group 0;\nfence.proxy.async.global;" ::: "memory");
        TS(75);
        if (!(NOMB & 2)) asm volatile("fence.release.gpu;" ::: "memory");
        flag_bump(g_cnt + C_Y + 32 * (b >> 4));
        TS(27);
        mbar_arrive(bars + 8 * B_YSIG);
        mbar_expect_tx(bars + 8 * B_YFULL, 20480);
        flag_wait(g_cnt + C_Y + 32 * hg, (lds32(sb + OFF_EPOCH) + 1) * 16);
        TS(24);
        tma_2d(sb + OFF_YT, &m.y, 128 * r, 80 * hg, bars + 8 * B_YFULL);
        tma_2d(sb + OFF_YT + 10240, &m.y, 128 * r + 64, 80 * hg, bars + 8 * B_YFULL);
      }
    }
  } else {
    asm volatile("setmaxnreg.inc.sync.aligned.u32 152;");
    if (wg < 2) {
      float acc[120];
#pragma unroll
      for (int i = 0; i < 120; i++) acc[i] = 0.f;
      const uint32_t da = desc_lo(sb + wg * 8192, 16), db = desc_lo(sb + ST_W, 8192), dc = desc_lo(sb + ST_WT, 2048);
      if (PW1) pin<120>(acc);
      if (PW1 == 2) mbar_wait(bars + 8 * B_FULL1, 0);
#pragma unroll 1
      for (int kb = 0; kb < 10; kb++) {
        mbar_wait(bars + 8 * (B_FULL1 + (kb & 3)), (kb >> 2) & 1);
        const uint32_t so = (kb & 3) * (STAGE_BYTES >> 4);
        wg_fence();
#pragma unroll
        for (int k = 0; k < 4; k++) {
          WgSST<192>::mma<HI_SW128, HI_SW128>(acc, da + so + 2 * k, db + so + 128 * k, 1);
          WgSST<48>::mma<HI_SW128, HI_SW32>(acc + 96, da + so + 2 * k, dc + so + 32 * k, 1);
        }
        wg_commit();
        wg_wait<1>();
        if (kb > 0 && lane == 0) mbar_arrive(bars + 8 * (kb == 4 ? B_E3 : B_EMPTY1 + ((kb - 1) & 3)));
      }
      mbar_wait(bars + 8 * B_EPOCH, 0);
      const uint32_t tag = lds32(sb + OFF_EPOCH) + 1;
      mbar_wait(bars + 8 * B_S3, 0);
      wg_wait<0>();
      pin<120>(acc);
      if (lane == 0) mbar_arrive(bars + 8 * B_P1);
      TSM(w == 0, 3 + wg);
      attention(acc, sb, b, wg, w, lane, tag);
    } else {
      const int tw = tid & 127, chl = 64 * (b & 1) + 8 * w + (lane >> 2);
      uint4* up = g_U + chl * U_PITCH + ((4 * (b >> 1) + (lane & 3)) ^ ((b >> 2) & 1));
      uint2 sw[10];
      uint32_t dv = 0;
      if (lane < 5) dv = __ldg(reinterpret_cast<const unsigned short*>(p.ssm_D) + 5 * b + lane);
#pragma unroll
      for (int i = 0; i < 10; i++) sw[i] = ldg64(reinterpret_cast<const uint2*>(p.shift_k) + chl + 128 * (i >> 1) + 32 * (i & 1));
      uint32_t tab[12];
      float tt[4];
      fft_tables(tab, tw);
      fft_twiddles(tt, tw);
      uint4 res[10];
#pragma unroll
      for (int i = 0; i < 10; i++) res[i] = make_uint4(0, 0, 0, 0);
#pragma unroll 1
      for (int slab = 0; slab < 5; slab++) {
#pragma unroll
        for (int i = 0; i < 8; i++) res[i] = res[i + 2];
        prep_slab(res + 8, sw, sb, slab, w, lane);
        TSIF(w == 0, 99 + 4 * slab);
#pragma unroll
        for (int i = 0; i < 8; i++) sw[i] = sw[i + 2];
      }
      TSIF(w == 0, 28);
      __syncwarp();
      if (lane == 0) mbar_arrive(bars + 8 * B_KVD + ((res[8].x ^ res[9].x) & p.zero));
      mbar_wait(bars + 8 * B_KVD, 0);
      fft_tables_store(tab, sb, tw);
      mbar_wait(bars + 8 * B_LAST, 0);
#pragma unroll
      for (int i = 0; i < 10; i++) up[(128 * (i >> 1) + 32 * (i & 1)) * U_PITCH] = res[i];
      __syncwarp();
      if (lane == 0) mbar_arrive(bars + 8 * B_PREP);
      TSIF(w == 0 && !U_TMA, 5);
      mbar_wait(bars + 8 * (G_AFTER ? B_USIG : B_LAST), 0);
      prep_gate(p, b, w, lane);
      __syncwarp();
      if (lane == 0) mbar_arrive(bars + 8 * B_GATE);
      TSIF(w == 0, 72);
      mbar_wait(bars + 8 * B_HB, 0);
      TSIF(w == 0, 2);
      const uint32_t ha = sb + U_BYTES + ((tw >> 3) * 16 + 8 + (tw & 7)) * 16;
      uint4 hv[5];
#pragma unroll
      for (int c = 0; c < 5; c++) hv[c] = lds128(ha + off_ch(c));
      __syncwarp();
#pragma unroll
      for (int c = 0; c < 5; c++) sts128((ha ^ 16) + off_ch(c), hv[c].x, hv[c].y, hv[c].z, hv[c].w);
      sts128(sb + OFF_TT + 16 * tw, __float_as_uint(tt[0]), __float_as_uint(tt[1]), __float_as_uint(tt[2]), __float_as_uint(tt[3]));
      if (tw < 5) asm volatile("st.shared.f32 [%0], %1;" ::"r"(sb + OFF_D + 4 * tw), "f"(bf_lo(dv) * 0.125f) : "memory");
      fence_async_smem();
      __syncwarp();
      if (lane == 0) mbar_arrive(bars + 8 * B_HA);
      TSIF(w == 0, 6);
    }

    FftConst fc;
    TSM(w == 0 && wg == 0, 104);
    mbar_wait(bars + 8 * B_HA, 0);
    fft_matrices(fc, sb, w, lane);
    TSM(w == 0 && wg == 0, 105);
    if (ATT_GATE && !H_EARLY) mbar_wait(bars + 8 * B_ATTN, 0);
    TSM(w == 0 && wg == 2, 124);
#pragma unroll 1
    for (uint32_t tasks = wg == 0 ? TASK0 : wg == 1 ? TASK1 : TASK2; tasks; tasks >>= 4) {
      const int c = (tasks & 7) - 1;
      conv_channel(fc, sb, c, wg, w, lane);
      if (lane == 0) mbar_arrive(bars + 8 * (B_YST + c));
      TSM(w == 0, 10 + c);
    }

    if (wg < 2) {
      const int g = lane >> 2;
      float acc[40];
#pragma unroll
      for (int i = 0; i < 40; i++) acc[i] = 0.f;
      const uint32_t da = desc_lo(sb + wg * 1024, 2048), db = desc_lo(sb, 2560);
      mbar_wait(bars + 8 * B_ATTN, 0);
      mbar_wait(bars + 8 * (B_YST + 3), 0);
      if (WO_GATE == 1) mbar_wait(bars + 8 * (B_YST + 4), 0);
      if (PW2) mbar_wait(bars + 8 * B_FULL2, 0);
      TSM(w == 0, 15 + wg);
#pragma unroll 1
      for (int j = 0; j < 8; j++) {
        mbar_wait(bars + 8 * (B_FULL2 + j), 0);
        const uint32_t oa = da + (off_o(j) >> 4), ob = db + (off_w(j) >> 4);
        wg_fence();
#pragma unroll
        for (int k = 0; k < 5; k++) WgSST<80>::mma<HI_NONE, HI_SW32>(acc, oa + 256 * k, ob + 32 * k, 1);
        wg_commit();
        wg_wait<1>();
        if (j >= 1 && j <= 4 && lane == 0) mbar_arrive(bars + 8 * (B_EMPTY2 + j - 1));
      }
      TSIF(w == 0 && wg == 0, 113);
      const int tr = 64 * wg + 16 * w + (lane & 15);
      const uint32_t fm = sb + OFF_QS + tr * 128, fx = (lane >> 4) ^ (tr & 7);
      const uint32_t ft = sb + OFF_QT + tr * 32 + (((lane >> 4) ^ (tr >> 2)) & 1) * 16;
      const float g0 = __uint_as_float(lds32(sb + OFF_GATE + (64 * wg + 16 * w + g) * 4));
      const float g1 = __uint_as_float(lds32(sb + OFF_GATE + (64 * wg + 16 * w + 8 + g) * 4));
      const uint32_t ga = pack2(g0, g0), gb = pack2(g1, g1);
      const uint32_t na = pack2(1.f - g0, 1.f - g0), nb = pack2(1.f - g1, 1.f - g1);

      wg_wait<0>();
      pin<40>(acc);
      TSM(w == 0, 17 + wg);
      uint32_t pb[20];
#pragma unroll
      for (int j = 0; j < 10; j++) {
        pb[2 * j] = bmul(na, pack2(acc[4 * j], acc[4 * j + 1]));
        pb[2 * j + 1] = bmul(nb, pack2(acc[4 * j + 2], acc[4 * j + 3]));
        asm volatile("" : "+r"(pb[2 * j]), "+r"(pb[2 * j + 1]));
      }
      const uint32_t ya = sb + OFF_YT + wg * 10240 + ((lane >> 4) * 8 + (lane & 7)) * 128 +
                          (((2 * w + (((lane >> 3) & 1) ^ wg)) ^ (lane & 7)) << 4);
      uint32_t qf[20];
      mbar_wait(bars + 8 * B_QF, 0);
#pragma unroll
      for (int j = 0; j < 5; j++) ldsm4(qf + 4 * j, j < 4 ? fm + ((fx ^ (2 * j)) << 4) : ft);
      mbar_wait(bars + 8 * B_YFULL, 0);
      TSM(w == 0 && wg == 0, 19);
#pragma unroll
      for (int j = 0; j < 5; j++) {
        uint32_t y[4];
        ldsm4t(y, ya + 2048 * j);
#pragma unroll
        for (int i = 0; i < 4; i++) qf[4 * j + i] = badd(bmul((i & 1) ? gb : ga, bmul(qf[4 * j + i], y[i])), pb[4 * j + i]);
      }
#pragma unroll
      for (int j = 0; j < 5; j++) stsm4(j < 4 ? fm + ((fx ^ (2 * j)) << 4) : ft, qf + 4 * j);
      fence_async_smem();
      __syncwarp();
      if (lane == 0) {
        const int row = 64 * wg + 16 * w;
        asm volatile("cp.async.bulk.tensor.2d.global.shared::cta.bulk_group [%0, {%2, %3}], [%1];"
                     ::"l"(&m.om), "r"(sb + OFF_QS + row * 128), "r"(80 * hg), "r"(128 * r + row) : "memory");
        asm volatile("cp.async.bulk.tensor.2d.global.shared::cta.bulk_group [%0, {%2, %3}], [%1];"
                     ::"l"(&m.ot), "r"(sb + OFF_QT + row * 32), "r"(80 * hg + 64), "r"(128 * r + row) : "memory");
        asm volatile("cp.async.bulk.commit_group;\ncp.async.bulk.wait_group.read 0;" ::: "memory");
      }
      TSM(true, 40 + 4 * wg + w);
      if (ENDBAR) asm volatile("bar.sync 15, 256;" ::: "memory");
    }
  }
}

typedef CUresult (*EncodeFn)(CUtensorMap*, CUtensorMapDataType, cuuint32_t, void*, const cuuint64_t*, const cuuint64_t*,
                             const cuuint32_t*, const cuuint32_t*, CUtensorMapInterleave, CUtensorMapSwizzle,
                             CUtensorMapL2promotion, CUtensorMapFloatOOBfill);

void encode(EncodeFn fn, CUtensorMap* tm, const void* base, int rank, const cuuint64_t* dims, const cuuint64_t* strides,
            const cuuint32_t* box, CUtensorMapSwizzle swz) {
  const cuuint32_t ones[3] = {1, 1, 1};
  fn(tm, CU_TENSOR_MAP_DATA_TYPE_BFLOAT16, rank, const_cast<void*>(base), dims, strides, box, ones,
     CU_TENSOR_MAP_INTERLEAVE_NONE, swz, CU_TENSOR_MAP_L2_PROMOTION_L2_128B, CU_TENSOR_MAP_FLOAT_OOB_FILL_NONE);
}

}

extern "C" void kernel_launch(void* const* d_in, const int* in_sizes, int n_in, void* d_out, int out_size) {
  (void)in_sizes; (void)n_in; (void)out_size;
  Params p;
  p.q = (const __nv_bfloat16*)d_in[0];
  p.k = (const __nv_bfloat16*)d_in[1];
  p.v = (const __nv_bfloat16*)d_in[2];
  p.shift_k = (const __nv_bfloat16*)d_in[3];
  p.ssm_k = (const __nv_bfloat16*)d_in[4];
  p.ssm_D = (const __nv_bfloat16*)d_in[5];
  p.wqkv = (const __nv_bfloat16*)d_in[7];
  p.wo = (const __nv_bfloat16*)d_in[8];
  p.gate_w = (const __nv_bfloat16*)d_in[9];
  p.out = (__nv_bfloat16*)d_out;
  p.zero = 0;

  static EncodeFn fn = nullptr;
  static void *yaddr = nullptr, *uaddr = nullptr;
  if (!fn) {
    cudaDriverEntryPointQueryResult qr;
    void* f = nullptr;
    cudaGetDriverEntryPoint("cuTensorMapEncodeTiled", &f, cudaEnableDefault, &qr);
    fn = (EncodeFn)f;
    cudaGetSymbolAddress(&yaddr, g_Y);
    cudaGetSymbolAddress(&uaddr, g_U);
    cudaFuncSetAttribute(fused_kernel, cudaFuncAttributeMaxDynamicSharedMemorySize, SMEM_BYTES);
  }
  Maps m;
  {
    const cuuint64_t dims[3] = {640, 1024, 2}, st[2] = {2560, 1280};
    const cuuint32_t box[3] = {64, 64, 2};
    encode(fn, &m.x, p.q, 3, dims, st, box, CU_TENSOR_MAP_SWIZZLE_128B);
  }
  {
    const cuuint64_t dims[3] = {640, 640, 3}, st[2] = {3840, 1280};
    const cuuint32_t box[3] = {64, 64, 3}, boxt[3] = {16, 64, 3};
    encode(fn, &m.wm, p.wqkv, 3, dims, st, box, CU_TENSOR_MAP_SWIZZLE_128B);
    encode(fn, &m.wt, p.wqkv, 3, dims, st, boxt, CU_TENSOR_MAP_SWIZZLE_32B);
  }
  {
    const cuuint64_t dims[3] = {64, 2048, 10}, st[2] = {1280, 128};
    const cuuint32_t boxk[3] = {64, 35, 1}, boxv[3] = {64, 32, 1};
    encode(fn, &m.k, p.k, 3, dims, st, boxk, CU_TENSOR_MAP_SWIZZLE_128B);
    encode(fn, &m.v, p.v, 3, dims, st, boxv, CU_TENSOR_MAP_SWIZZLE_128B);
  }
  {
    const cuuint64_t dims[3] = {16, 640, 40}, st[2] = {1280, 32};
    const cuuint32_t box[3] = {16, 40, 5};
    encode(fn, &m.wo, p.wo, 3, dims, st, box, CU_TENSOR_MAP_SWIZZLE_32B);
  }
  {
    const cuuint64_t dims[2] = {2048, 640}, st[1] = {Y_PITCH * 16};
    const cuuint32_t box[2] = {64, 80};
    encode(fn, &m.y, yaddr, 2, dims, st, box, CU_TENSOR_MAP_SWIZZLE_128B);
    const cuuint64_t stu[1] = {U_PITCH * 16};
    const cuuint32_t boxu[2] = {32, 64};
    encode(fn, &m.u, uaddr, 2, dims, stu, boxu, CU_TENSOR_MAP_SWIZZLE_NONE);
  }
  {
    const cuuint64_t dims[2] = {640, 2048}, st[1] = {1280};
    const cuuint32_t bqm[2] = {64, 128}, bqt[2] = {16, 128}, bom[2] = {64, 16}, bot[2] = {16, 16};
    encode(fn, &m.qm, p.q, 2, dims, st, bqm, CU_TENSOR_MAP_SWIZZLE_128B);
    encode(fn, &m.qt, p.q, 2, dims, st, bqt, CU_TENSOR_MAP_SWIZZLE_32B);
    encode(fn, &m.om, p.out, 2, dims, st, bom, CU_TENSOR_MAP_SWIZZLE_128B);
    encode(fn, &m.ot, p.out, 2, dims, st, bot, CU_TENSOR_MAP_SWIZZLE_32B);
  }
  fused_kernel<<<NCTA, NTHR, SMEM_BYTES>>>(m, p);
}
```

```cpp
#include <cuda.h>
#include <cuda_bf16.h>
#include <cuda_runtime.h>
#include <stdint.h>

namespace {

constexpr int SEQ = 2048, DIM = 640, NCTA = 128, NTHR = 512;

#define TRIG_KB 9
#define KV_KB 2
#define DEV_EXIT 0
#define ATT_GATE 1
#define G_AFTER 0
#define FENCE_LO 0
#define FENCE_HI 0
#define PW1 2
#define PW2 1
#define ENDBAR 0
#define PAD_KB 0
#define Y_ALIAS 1
#define H_EARLY 1
#define NOMB 0
#define SRC_ROT 0
#define WAIT_NS 0
#define WB_TRIG B_USIG
#define G_POS 0
#define TAILF 1
#define T_ISSUE 384
#define T_PF 416
#define T_INIT 448
#define ATT_MERGE 0
#define BMAP 1
#define PRE2 1
#define KV_MIX 0
#define O_DEFER 0
#define TASK0 0x52
#define TASK1 0x3
#define TASK2 0x41
#define HALO_FIRST 1
#define PREV_EARLY 0
#define PRE2G PRE2
#define GOOD_WAIT 0
#define ACQ 0
#define U_TMA 0
#define U_GATE 0
#define RF_GATE 0
#define WO_TRIG B_WST
#define WL_TRIG B_WOP
#define WO_GATE 1

constexpr uint32_t STAGE_BYTES = 47104, ST_W = 16384, ST_WT = 40960;
constexpr uint32_t O_BYTES = 20480, WO_BYTES = 12800;
constexpr uint32_t OFF_OA = 0;
constexpr uint32_t OFF_QS = 3 * O_BYTES, OFF_QT = OFF_QS + 16384;
constexpr uint32_t OFF_WC = 81920;
constexpr uint32_t OFF_WA = 94720;
constexpr uint32_t OFF_GATE = 145920;
constexpr uint32_t OFF_TT = 146432;
constexpr uint32_t OFF_KVX = 148480;
constexpr uint32_t OFF_CH3 = 163840;
constexpr uint32_t CH_BYTES = 12288, U_BYTES = 4096;
constexpr uint32_t OFF_FT = 225280, OFF_GT = 229376;
constexpr uint32_t OFF_CH0 = 188416;
constexpr uint32_t OFF_KVS = OFF_CH0, KVS_V = 4480, KVS_BYTES = 8576;
constexpr uint32_t OFF_WS = OFF_WA;
__device__ __forceinline__ uint32_t off_us(int s) { return OFF_CH0 + 4096 * ((0x65320 >> (4 * s)) & 7); }
constexpr uint32_t OFF_YT = 163840;
constexpr uint32_t OFF_BAR = 231936;
constexpr uint32_t SMEM_BYTES = OFF_BAR + 512;

enum : uint32_t {
  B_FULL1 = 0, B_EMPTY1 = 4, B_S3 = 7, B_FULL2 = 52, B_EMPTY2 = 13, B_U = 8, B_GATE = 12, B_HA = 19, B_HB = 20,
  B_ATTN = 21, B_C34 = 22, B_CONV = 23, B_YFULL = 24, B_EPOCH = 25, B_PREP = 26, B_P1 = 27, B_LAST = 28,
  B_E3 = 29, B_OSIG = 30, B_WOP = 31, B_USIG = 32, B_WST = 33, B_KV = 34, B_KVD = 39, B_QF = 17, B_YST = 40,
  B_US = 45, B_YSIG = 50
};
constexpr uint32_t OFF_EPOCH = OFF_BAR + 8 * 51, OFF_D = OFF_BAR + 8 * 60;
__device__ __forceinline__ uint32_t off_o(int j) { return j < 4 ? OFF_OA + j * O_BYTES : j < 6 ? OFF_CH0 + (j - 4) * O_BYTES : OFF_OA + (j - 6) * O_BYTES; }
__device__ __forceinline__ uint32_t off_w(int j) { return j < 4 ? OFF_WA + j * WO_BYTES : j == 4 ? OFF_KVX : j == 5 ? OFF_WC : OFF_WA + (j - 6) * WO_BYTES; }
__device__ __forceinline__ int step_src(int hg, int j) { return SRC_ROT ? (hg + j) & 7 : j == 0 ? hg : j <= hg ? j - 1 : j; }
__device__ __forceinline__ bool tail_first(int hg) { return TAILF && (hg & 3) == 3; }
__device__ __forceinline__ uint32_t off_ch(int c) { return (c < 3 ? OFF_CH0 : OFF_CH3 - 3 * CH_BYTES) + c * CH_BYTES; }

#define U_PITCH 264
__device__ __align__(1024) uint4 g_U[DIM * U_PITCH];
__device__ uint4 g_O[NCTA * 1280];
#define g_Y g_U
constexpr int Y_PITCH = U_PITCH;
__device__ uint4 g_WO[64 * 800];
__device__ uint4 g_halo[NCTA * 2 * 7 * 32];
__device__ float g_gate[SEQ + PAD_KB * 256];
__device__ unsigned g_cnt[32 * (1 + 2 * 16 + 8 + NCTA)];
constexpr int C_LAUNCH = 0, C_PREP = 32, C_Y = 32 * 17, C_W = 32 * 33, C_O = 32 * 41;

#define TSM(cond, slot) do { } while (0)
#define TSIF(cond, slot) do { if (__LINE__ >= FENCE_LO && __LINE__ < FENCE_HI) sched_fence(); } while (0)
__device__ __forceinline__ void sched_fence() {
  asm volatile("{\n.reg .pred p;\n.reg .u32 c;\nmov.u32 c, %%clock;\nsetp.eq.u32 p, c, 0;\n@p st.shared.u32 [%0], c;\n}"
               ::"r"(1024 + OFF_EPOCH + 4) : "memory");
}
#define TS(slot) TSIF(true, slot)

struct Params {
  const __nv_bfloat16 *q, *k, *v, *shift_k, *ssm_k, *ssm_D, *wqkv, *wo, *gate_w;
  __nv_bfloat16* out;
  uint32_t zero;
};

#define POLL_NS 0
constexpr int SPIN_LIMIT = 1 << 17;

__device__ __forceinline__ void mbar_init(uint32_t bar, uint32_t count) {
  asm volatile("mbarrier.init.shared::cta.b64 [%0], %1;" ::"r"(bar), "r"(count) : "memory");
}
__device__ __forceinline__ void mbar_expect_tx(uint32_t bar, uint32_t bytes) {
  asm volatile("mbarrier.arrive.expect_tx.shared::cta.b64 _, [%0], %1;" ::"r"(bar), "r"(bytes) : "memory");
}
__device__ __forceinline__ void mbar_arrive(uint32_t bar) {
  asm volatile("mbarrier.arrive.shared::cta.b64 _, [%0];" ::"r"(bar) : "memory");
}
__device__ __forceinline__ void mbar_wait(uint32_t bar, uint32_t parity) {
  uint32_t ok;
  int spins = 0;
  do {
    if (WAIT_NS)
      asm volatile("{\n.reg .pred p;\nmbarrier.try_wait.parity.shared::cta.b64 p, [%1], %2, %3;\nselp.b32 %0, 1, 0, p;\n}"
                   : "=r"(ok) : "r"(bar), "r"(parity), "r"(WAIT_NS) : "memory");
    else
      asm volatile("{\n.reg .pred p;\nmbarrier.try_wait.parity.shared::cta.b64 p, [%1], %2;\nselp.b32 %0, 1, 0, p;\n}"
                   : "=r"(ok) : "r"(bar), "r"(parity) : "memory");
    if (++spins > SPIN_LIMIT) break;
  } while (!ok);
}
__device__ __forceinline__ unsigned flag_read(const unsigned* p) {
  unsigned v;
  asm volatile("ld.relaxed.gpu.global.u32 %0, [%1];" : "=r"(v) : "l"(p) : "memory");
  return v;
}
__device__ __forceinline__ void flag_poll(const unsigned* p, unsigned target) {
  unsigned v;
  int spins = 0;
  do {
    if (POLL_NS && spins) __nanosleep(POLL_NS);
    asm volatile("ld.relaxed.gpu.global.u32 %0, [%1];" : "=r"(v) : "l"(p) : "memory");
    if (++spins > SPIN_LIMIT) break;
  } while ((int)(v - target) < 0);
}
__device__ __forceinline__ void flag_wait(const unsigned* p, unsigned target) {
  flag_poll(p, target);
  if (ACQ) asm volatile("fence.acquire.gpu;\nfence.proxy.async.global;" ::: "memory");
}
__device__ __forceinline__ void flag_signal(unsigned* p, int n, int lane) {
  if (lane == 0) asm volatile("fence.release.gpu;" ::: "memory");
  __syncwarp();
  if (lane < n) asm volatile("red.relaxed.gpu.global.add.u32 [%0], 1;" ::"l"(p + 32 * lane) : "memory");
}
__device__ __forceinline__ void flag_bump(unsigned* p) {
  asm volatile("red.relaxed.gpu.global.add.u32 [%0], 1;" ::"l"(p) : "memory");
}
__device__ __forceinline__ void fence_async_smem() { asm volatile("fence.proxy.async.shared::cta;" ::: "memory"); }
__device__ __forceinline__ void wg_sync(int id) { asm volatile("bar.sync %0, 128;" ::"r"(id) : "memory"); }

__device__ __forceinline__ void tma_2d(uint32_t dst, const CUtensorMap* tm, int c0, int c1, uint32_t bar) {
  asm volatile("cp.async.bulk.tensor.2d.shared::cluster.global.mbarrier::complete_tx::bytes [%0], [%1, {%3, %4}], [%2];"
               ::"r"(dst), "l"(tm), "r"(bar), "r"(c0), "r"(c1) : "memory");
}
__device__ __forceinline__ void tma_3d(uint32_t dst, const CUtensorMap* tm, int c0, int c1, int c2, uint32_t bar) {
  asm volatile("cp.async.bulk.tensor.3d.shared::cluster.global.mbarrier::complete_tx::bytes [%0], [%1, {%3, %4, %5}], [%2];"
               ::"r"(dst), "l"(tm), "r"(bar), "r"(c0), "r"(c1), "r"(c2) : "memory");
}
__device__ __forceinline__ void bulk_load(uint32_t dst, const void* src, uint32_t bytes, uint32_t bar) {
  asm volatile("cp.async.bulk.shared::cluster.global.mbarrier::complete_tx::bytes [%0], [%1], %2, [%3];"
               ::"r"(dst), "l"(src), "r"(bytes), "r"(bar) : "memory");
}
__device__ __forceinline__ void tm_prefetch(const CUtensorMap* tm) {
  asm volatile("prefetch.tensormap [%0];" ::"l"(tm) : "memory");
}

__device__ __forceinline__ void wg_fence() { asm volatile("wgmma.fence.sync.aligned;" ::: "memory"); }
__device__ __forceinline__ void wg_commit() { asm volatile("wgmma.commit_group.sync.aligned;" ::: "memory"); }
template <int N> __device__ __forceinline__ void wg_wait() { asm volatile("wgmma.wait_group.sync.aligned %0;" ::"n"(N) : "memory"); }
__device__ __forceinline__ uint32_t desc_lo(uint32_t addr, uint32_t lbo) { return ((addr & 0x3FFFF) >> 4) | ((lbo >> 4) << 16); }
constexpr uint32_t desc_hi(uint32_t sbo, uint32_t swz) { return (sbo >> 4) | (swz << 30); }
constexpr uint32_t HI_SW128 = desc_hi(1024, 1), HI_SW64 = desc_hi(512, 2), HI_SW32 = desc_hi(256, 3), HI_NONE = desc_hi(128, 0);
template <int N> __device__ __forceinline__ void pin(float* d) {
#pragma unroll
  for (int i = 0; i < N; i++) asm volatile("" : "+f"(d[i])::"memory");
}

__device__ __forceinline__ uint32_t lds32(uint32_t a) {
  uint32_t v;
  asm volatile("ld.volatile.shared.u32 %0, [%1];" : "=r"(v) : "r"(a) : "memory");
  return v;
}
__device__ __forceinline__ uint4 ldg128(const void* a) {
  uint4 v;
  asm volatile("ld.global.nc.v4.u32 {%0, %1, %2, %3}, [%4];" : "=r"(v.x), "=r"(v.y), "=r"(v.z), "=r"(v.w) : "l"(a) : "memory");
  return v;
}
__device__ __forceinline__ uint2 ldg64(const void* a) {
  uint2 v;
  asm volatile("ld.global.nc.v2.u32 {%0, %1}, [%2];" : "=r"(v.x), "=r"(v.y) : "l"(a) : "memory");
  return v;
}
__device__ __forceinline__ void ldsm4(uint32_t* r, uint32_t a) {
  asm volatile("ldmatrix.sync.aligned.m8n8.x4.shared.b16 {%0, %1, %2, %3}, [%4];"
               : "=r"(r[0]), "=r"(r[1]), "=r"(r[2]), "=r"(r[3]) : "r"(a) : "memory");
}
__device__ __forceinline__ void ldsm4t(uint32_t* r, uint32_t a) {
  asm volatile("ldmatrix.sync.aligned.m8n8.x4.trans.shared.b16 {%0, %1, %2, %3}, [%4];"
               : "=r"(r[0]), "=r"(r[1]), "=r"(r[2]), "=r"(r[3]) : "r"(a) : "memory");
}
__device__ __forceinline__ uint4 lds128(uint32_t a) {
  uint4 v;
  asm volatile("ld.shared.v4.u32 {%0, %1, %2, %3}, [%4];" : "=r"(v.x), "=r"(v.y), "=r"(v.z), "=r"(v.w) : "r"(a) : "memory");
  return v;
}
__device__ __forceinline__ void sts128(uint32_t a, uint32_t x, uint32_t y, uint32_t z, uint32_t w) {
  asm volatile("st.shared.v4.u32 [%0], {%1, %2, %3, %4};" ::"r"(a), "r"(x), "r"(y), "r"(z), "r"(w) : "memory");
}
__device__ __forceinline__ void stsm4(uint32_t a, const uint32_t* r) {
  asm volatile("stmatrix.sync.aligned.m8n8.x4.shared.b16 [%0], {%1, %2, %3, %4};" ::"r"(a), "r"(r[0]), "r"(r[1]), "r"(r[2]), "r"(r[3]) : "memory");
}
__device__ __forceinline__ void stsm4t(uint32_t a, const uint32_t* r) {
  asm volatile("stmatrix.sync.aligned.m8n8.x4.trans.shared.b16 [%0], {%1, %2, %3, %4};" ::"r"(a), "r"(r[0]), "r"(r[1]), "r"(r[2]), "r"(r[3]) : "memory");
}
__device__ __forceinline__ uint32_t pack2(float lo, float hi) {
  uint32_t r;
  asm("cvt.rn.bf16x2.f32 %0, %1, %2;" : "=r"(r) : "f"(hi), "f"(lo));
  return r;
}
__device__ __forceinline__ uint32_t movm(uint32_t a) {
  uint32_t d;
  asm volatile("movmatrix.sync.aligned.m8n8.trans.b16 %0, %1;" : "=r"(d) : "r"(a));
  return d;
}
__device__ __forceinline__ uint32_t bmul(uint32_t a, uint32_t b) {
  uint32_t d;
  asm("mul.rn.bf16x2 %0, %1, %2;" : "=r"(d) : "r"(a), "r"(b));
  return d;
}
__device__ __forceinline__ uint32_t badd(uint32_t a, uint32_t b) {
  uint32_t d;
  asm("add.rn.bf16x2 %0, %1, %2;" : "=r"(d) : "r"(a), "r"(b));
  return d;
}
__device__ __forceinline__ float bf_lo(uint32_t x) { return __uint_as_float(x << 16); }
__device__ __forceinline__ float bf_hi(uint32_t x) { return __uint_as_float(x & 0xFFFF0000u); }
__device__ __forceinline__ float ex2(float x) {
  float y;
  asm("ex2.approx.ftz.f32 %0, %1;" : "=f"(y) : "f"(x));
  return y;
}
__device__ __forceinline__ float rcp(float x) {
  float y;
  asm("rcp.approx.ftz.f32 %0, %1;" : "=f"(y) : "f"(x));
  return y;
}
__device__ __forceinline__ void mma16816(float* d, uint32_t a0, uint32_t a1, uint32_t a2, uint32_t a3, uint32_t b0, uint32_t b1) {
  asm volatile("mma.sync.aligned.m16n8k16.row.col.f32.bf16.bf16.f32 {%0, %1, %2, %3}, {%4, %5, %6, %7}, {%8, %9}, {%0, %1, %2, %3};"
               : "+f"(d[0]), "+f"(d[1]), "+f"(d[2]), "+f"(d[3])
               : "r"(a0), "r"(a1), "r"(a2), "r"(a3), "r"(b0), "r"(b1));
}
__device__ __forceinline__ void mma1688(float* d, uint32_t a0, uint32_t a1, uint32_t b0) {
  asm volatile("mma.sync.aligned.m16n8k8.row.col.f32.bf16.bf16.f32 {%0, %1, %2, %3}, {%4, %5}, {%6}, {%0, %1, %2, %3};"
               : "+f"(d[0]), "+f"(d[1]), "+f"(d[2]), "+f"(d[3])
               : "r"(a0), "r"(a1), "r"(b0));
}

template <int N> struct WgRS;
template <int N> struct WgSST;
template <> struct WgRS<32> {
  template <uint32_t HB>
  static __device__ __forceinline__ void mma(float* d, const uint32_t* a, uint32_t db) {
    asm volatile("{\n.reg .pred p;\n.reg .b64 db;\nsetp.ne.b32 p, %22, 0;\n"
      "mov.b64 db, {%20, %21};\n"
      "wgmma.mma_async.sync.aligned.m64n32k16.f32.bf16.bf16 {"
      "%0, %1, %2, %3, %4, %5, %6, %7, %8, %9, %10, %11, %12, %13, %14, %15"
      "}, {%16, %17, %18, %19}, db, p, 1, 1, 1;\n}\n"
      : "+f"(d[0]), "+f"(d[1]), "+f"(d[2]), "+f"(d[3]), "+f"(d[4]), "+f"(d[5]), "+f"(d[6]), "+f"(d[7]),
        "+f"(d[8]), "+f"(d[9]), "+f"(d[10]), "+f"(d[11]), "+f"(d[12]), "+f"(d[13]), "+f"(d[14]), "+f"(d[15])
      : "r"(a[0]), "r"(a[1]), "r"(a[2]), "r"(a[3]), "r"(db), "n"(HB), "n"(1));
  }
  template <uint32_t HB>
  static __device__ __forceinline__ void set(float* d, const uint32_t* a, uint32_t db) {
    asm volatile("{\n.reg .pred p;\n.reg .b64 db;\nsetp.ne.b32 p, %22, 0;\n"
      "mov.b64 db, {%20, %21};\n"
      "wgmma.mma_async.sync.aligned.m64n32k16.f32.bf16.bf16 {"
      "%0, %1, %2, %3, %4, %5, %6, %7, %8, %9, %10, %11, %12, %13, %14, %15"
      "}, {%16, %17, %18, %19}, db, p, 1, 1, 1;\n}\n"
      : "=f"(d[0]), "=f"(d[1]), "=f"(d[2]), "=f"(d[3]), "=f"(d[4]), "=f"(d[5]), "=f"(d[6]), "=f"(d[7]),
        "=f"(d[8]), "=f"(d[9]), "=f"(d[10]), "=f"(d[11]), "=f"(d[12]), "=f"(d[13]), "=f"(d[14]), "=f"(d[15])
      : "r"(a[0]), "r"(a[1]), "r"(a[2]), "r"(a[3]), "r"(db), "n"(HB), "n"(0));
  }
};
template <> struct WgRS<64> {
  template <uint32_t HB>
  static __device__ __forceinline__ void mma(float* d, const uint32_t* a, uint32_t db) {
    asm volatile("{\n.reg .pred p;\n.reg .b64 db;\nsetp.ne.b32 p, %38, 0;\n"
      "mov.b64 db, {%36, %37};\n"
      "wgmma.mma_async.sync.aligned.m64n64k16.f32.bf16.bf16 {"
      "%0, %1, %2, %3, %4, %5, %6, %7, %8, %9, %10, %11, %12, %13, %14, %15, "
      "%16, %17, %18, %19, %20, %21, %22, %23, %24, %25, %26, %27, %28, %29, %30, %31"
      "}, {%32, %33, %34, %35}, db, p, 1, 1, 1;\n}\n"
      : "+f"(d[0]), "+f"(d[1]), "+f"(d[2]), "+f"(d[3]), "+f"(d[4]), "+f"(d[5]), "+f"(d[6]), "+f"(d[7]),
        "+f"(d[8]), "+f"(d[9]), "+f"(d[10]), "+f"(d[11]), "+f"(d[12]), "+f"(d[13]), "+f"(d[14]), "+f"(d[15]),
        "+f"(d[16]), "+f"(d[17]), "+f"(d[18]), "+f"(d[19]), "+f"(d[20]), "+f"(d[21]), "+f"(d[22]), "+f"(d[23]),
        "+f"(d[24]), "+f"(d[25]), "+f"(d[26]), "+f"(d[27]), "+f"(d[28]), "+f"(d[29]), "+f"(d[30]), "+f"(d[31])
      : "r"(a[0]), "r"(a[1]), "r"(a[2]), "r"(a[3]), "r"(db), "n"(HB), "n"(1));
  }
  template <uint32_t HB>
  static __device__ __forceinline__ void set(float* d, const uint32_t* a, uint32_t db) {
    asm volatile("{\n.reg .pred p;\n.reg .b64 db;\nsetp.ne.b32 p, %38, 0;\n"
      "mov.b64 db, {%36, %37};\n"
      "wgmma.mma_async.sync.aligned.m64n64k16.f32.bf16.bf16 {"
      "%0, %1, %2, %3, %4, %5, %6, %7, %8, %9, %10, %11, %12, %13, %14, %15, "
      "%16, %17, %18, %19, %20, %21, %22, %23, %24, %25, %26, %27, %28, %29, %30, %31"
      "}, {%32, %33, %34, %35}, db, p, 1, 1, 1;\n}\n"
      : "=f"(d[0]), "=f"(d[1]), "=f"(d[2]), "=f"(d[3]), "=f"(d[4]), "=f"(d[5]), "=f"(d[6]), "=f"(d[7]),
        "=f"(d[8]), "=f"(d[9]), "=f"(d[10]), "=f"(d[11]), "=f"(d[12]), "=f"(d[13]), "=f"(d[14]), "=f"(d[15]),
        "=f"(d[16]), "=f"(d[17]), "=f"(d[18]), "=f"(d[19]), "=f"(d[20]), "=f"(d[21]), "=f"(d[22]), "=f"(d[23]),
        "=f"(d[24]), "=f"(d[25]), "=f"(d[26]), "=f"(d[27]), "=f"(d[28]), "=f"(d[29]), "=f"(d[30]), "=f"(d[31])
      : "r"(a[0]), "r"(a[1]), "r"(a[2]), "r"(a[3]), "r"(db), "n"(HB), "n"(0));
  }
};
template <> struct WgSST<48> {
  template <uint32_t HA, uint32_t HB>
  static __device__ __forceinline__ void mma(float* d, uint32_t da, uint32_t db, int sc) {
    asm volatile("{\n.reg .pred p;\n.reg .b64 da, db;\nsetp.ne.b32 p, %28, 0;\n"
      "mov.b64 da, {%24, %25};\nmov.b64 db, {%26, %27};\n"
      "wgmma.mma_async.sync.aligned.m64n48k16.f32.bf16.bf16 {"
      "%0, %1, %2, %3, %4, %5, %6, %7, %8, %9, %10, %11, %12, %13, %14, %15, "
      "%16, %17, %18, %19, %20, %21, %22, %23"
      "}, da, db, p, 1, 1, 0, 1;\n}\n"
      : "+f"(d[0]), "+f"(d[1]), "+f"(d[2]), "+f"(d[3]), "+f"(d[4]), "+f"(d[5]), "+f"(d[6]), "+f"(d[7]),
        "+f"(d[8]), "+f"(d[9]), "+f"(d[10]), "+f"(d[11]), "+f"(d[12]), "+f"(d[13]), "+f"(d[14]), "+f"(d[15]),
        "+f"(d[16]), "+f"(d[17]), "+f"(d[18]), "+f"(d[19]), "+f"(d[20]), "+f"(d[21]), "+f"(d[22]), "+f"(d[23])
      : "r"(da), "n"(HA), "r"(db), "n"(HB), "r"(sc));
  }
};
template <> struct WgSST<80> {
  template <uint32_t HA, uint32_t HB>
  static __device__ __forceinline__ void mma(float* d, uint32_t da, uint32_t db, int sc) {
    asm volatile("{\n.reg .pred p;\n.reg .b64 da, db;\nsetp.ne.b32 p, %44, 0;\n"
      "mov.b64 da, {%40, %41};\nmov.b64 db, {%42, %43};\n"
      "wgmma.mma_async.sync.aligned.m64n80k16.f32.bf16.bf16 {"
      "%0, %1, %2, %3, %4, %5, %6, %7, %8, %9, %10, %11, %12, %13, %14, %15, "
      "%16, %17, %18, %19, %20, %21, %22, %23, %24, %25, %26, %27, %28, %29, %30, %31, "
      "%32, %33, %34, %35, %36, %37, %38, %39"
      "}, da, db, p, 1, 1, 0, 1;\n}\n"
      : "+f"(d[0]), "+f"(d[1]), "+f"(d[2]), "+f"(d[3]), "+f"(d[4]), "+f"(d[5]), "+f"(d[6]), "+f"(d[7]),
        "+f"(d[8]), "+f"(d[9]), "+f"(d[10]), "+f"(d[11]), "+f"(d[12]), "+f"(d[13]), "+f"(d[14]), "+f"(d[15]),
        "+f"(d[16]), "+f"(d[17]), "+f"(d[18]), "+f"(d[19]), "+f"(d[20]), "+f"(d[21]), "+f"(d[22]), "+f"(d[23]),
        "+f"(d[24]), "+f"(d[25]), "+f"(d[26]), "+f"(d[27]), "+f"(d[28]), "+f"(d[29]), "+f"(d[30]), "+f"(d[31]),
        "+f"(d[32]), "+f"(d[33]), "+f"(d[34]), "+f"(d[35]), "+f"(d[36]), "+f"(d[37]), "+f"(d[38]), "+f"(d[39])
      : "r"(da), "n"(HA), "r"(db), "n"(HB), "r"(sc));
  }
};
template <> struct WgSST<192> {
  template <uint32_t HA, uint32_t HB>
  static __device__ __forceinline__ void mma(float* d, uint32_t da, uint32_t db, int sc) {
    asm volatile("{\n.reg .pred p;\n.reg .b64 da, db;\nsetp.ne.b32 p, %100, 0;\n"
      "mov.b64 da, {%96, %97};\nmov.b64 db, {%98, %99};\n"
      "wgmma.mma_async.sync.aligned.m64n192k16.f32.bf16.bf16 {"
      "%0, %1, %2, %3, %4, %5, %6, %7, %8, %9, %10, %11, %12, %13, %14, %15, "
      "%16, %17, %18, %19, %20, %21, %22, %23, %24, %25, %26, %27, %28, %29, %30, %31, "
      "%32, %33, %34, %35, %36, %37, %38, %39, %40, %41, %42, %43, %44, %45, %46, %47, "
      "%48, %49, %50, %51, %52, %53, %54, %55, %56, %57, %58, %59, %60, %61, %62, %63, "
      "%64, %65, %66, %67, %68, %69, %70, %71, %72, %73, %74, %75, %76, %77, %78, %79, "
      "%80, %81, %82, %83, %84, %85, %86, %87, %88, %89, %90, %91, %92, %93, %94, %95"
      "}, da, db, p, 1, 1, 0, 1;\n}\n"
      : "+f"(d[0]), "+f"(d[1]), "+f"(d[2]), "+f"(d[3]), "+f"(d[4]), "+f"(d[5]), "+f"(d[6]), "+f"(d[7]),
        "+f"(d[8]), "+f"(d[9]), "+f"(d[10]), "+f"(d[11]), "+f"(d[12]), "+f"(d[13]), "+f"(d[14]), "+f"(d[15]),
        "+f"(d[16]), "+f"(d[17]), "+f"(d[18]), "+f"(d[19]), "+f"(d[20]), "+f"(d[21]), "+f"(d[22]), "+f"(d[23]),
        "+f"(d[24]), "+f"(d[25]), "+f"(d[26]), "+f"(d[27]), "+f"(d[28]), "+f"(d[29]), "+f"(d[30]), "+f"(d[31]),
        "+f"(d[32]), "+f"(d[33]), "+f"(d[34]), "+f"(d[35]), "+f"(d[36]), "+f"(d[37]), "+f"(d[38]), "+f"(d[39]),
        "+f"(d[40]), "+f"(d[41]), "+f"(d[42]), "+f"(d[43]), "+f"(d[44]), "+f"(d[45]), "+f"(d[46]), "+f"(d[47]),
        "+f"(d[48]), "+f"(d[49]), "+f"(d[50]), "+f"(d[51]), "+f"(d[52]), "+f"(d[53]), "+f"(d[54]), "+f"(d[55]),
        "+f"(d[56]), "+f"(d[57]), "+f"(d[58]), "+f"(d[59]), "+f"(d[60]), "+f"(d[61]), "+f"(d[62]), "+f"(d[63]),
        "+f"(d[64]), "+f"(d[65]), "+f"(d[66]), "+f"(d[67]), "+f"(d[68]), "+f"(d[69]), "+f"(d[70]), "+f"(d[71]),
        "+f"(d[72]), "+f"(d[73]), "+f"(d[74]), "+f"(d[75]), "+f"(d[76]), "+f"(d[77]), "+f"(d[78]), "+f"(d[79]),
        "+f"(d[80]), "+f"(d[81]), "+f"(d[82]), "+f"(d[83]), "+f"(d[84]), "+f"(d[85]), "+f"(d[86]), "+f"(d[87]),
        "+f"(d[88]), "+f"(d[89]), "+f"(d[90]), "+f"(d[91]), "+f"(d[92]), "+f"(d[93]), "+f"(d[94]), "+f"(d[95])
      : "r"(da), "n"(HA), "r"(db), "n"(HB), "r"(sc));
  }
};

struct FftConst {
  uint32_t f[2][4], fi[4][4];
  float ta[4], tb[4];
};
__device__ __forceinline__ void cis(int m, float scale, float& c, float& s) {
  const float a = (float)m * (-6.283185307179586f * scale);
  c = __cosf(a);
  s = __sinf(a);
}
__device__ __forceinline__ void fft_tables(uint32_t (&v)[12], int tw) {
  const int row = tw >> 2, ch = tw & 3;
#pragma unroll
  for (int i = 0; i < 4; i++) {
    float c[2], s[2], x[2];
#pragma unroll
    for (int e = 0; e < 2; e++) {
      cis((((32 * (8 * ch + 2 * i + e) + 15) * (4 * row - 63) + 2048) & 4095) - 2048, 1.f / 4096, c[e], s[e]);
      float gc, gs;
      cis((((row & 15) * (8 * (ch & 1) + 2 * i + e) + 8) & 15) - 8, 1.f / 16, gc, gs);
      x[e] = (row >> 4) == (ch >> 1) ? gc : (ch >> 1) ? gs : -gs;
    }
    v[i] = pack2(c[0] * 0.125f, c[1] * 0.125f);
    v[4 + i] = pack2(s[0] * 0.125f, s[1] * 0.125f);
    v[8 + i] = pack2(x[0], x[1]);
  }
#pragma unroll
  for (int i = 0; i < 12; i++) asm volatile("" : "+r"(v[i]));
}
__device__ __forceinline__ void fft_tables_store(const uint32_t (&v)[12], uint32_t sb, int tw) {
  const int row = tw >> 2;
  const uint32_t x = ((tw ^ (row >> 1)) & 3) << 4, a = sb + OFF_FT + (16 * (row >> 3) + (row & 7)) * 64 + x;
  sts128(a, v[0], v[1], v[2], v[3]);
  sts128(a + 512, v[4], v[5], v[6], v[7]);
  sts128(sb + OFF_GT + row * 64 + x, v[8], v[9], v[10], v[11]);
}
__device__ __forceinline__ void fft_twiddles(float (&v)[4], int tw) {
#pragma unroll
  for (int i = 0; i < 2; i++) {
    float c, s;
    cis((2 * (2 * (tw & 3) + i) - 15) * (4 * (tw >> 2) - 63), 1.f / 4096, c, s);
    v[2 * i] = __fdividef(-s, 1.f + c);
    v[2 * i + 1] = s;
  }
  pin<4>(v);
}
__device__ __forceinline__ void fft_matrices(FftConst& k, uint32_t sb, int w, int lane) {
  const uint32_t x = (lane >> 1) & 3;
  const uint4 t0 = lds128(sb + OFF_TT + 512 * w + 16 * lane), t1 = lds128(sb + OFF_TT + 512 * w + 16 * (lane ^ 3));
  k.ta[0] = __uint_as_float(t0.x); k.tb[0] = __uint_as_float(t0.y); k.ta[1] = __uint_as_float(t0.z); k.tb[1] = __uint_as_float(t0.w);
  k.ta[3] = __uint_as_float(t1.x); k.tb[3] = __uint_as_float(t1.y); k.ta[2] = __uint_as_float(t1.z); k.tb[2] = __uint_as_float(t1.w);
#pragma unroll
  for (int i = 0; i < 2; i++) {
    ldsm4(k.f[i], sb + OFF_FT + (16 * w + (lane & 15)) * 64 + (((2 * i + (lane >> 4)) ^ x) << 4));
    ldsm4t(k.fi[i], sb + OFF_FT + (32 * i + lane) * 64 + ((w ^ x) << 4));
#pragma unroll
    for (int j = 0; j < 4; j++) {
      k.fi[2 + i][j] = (j & 1) ? k.fi[i][j - 1] ^ 0x80008000u : k.fi[i][j + 1];
      asm volatile("" : "+r"(k.fi[2 + i][j]));
    }
  }
}
__device__ __forceinline__ void rot(bool inv, float& x, float& y, float a, float b) {
  x = fmaf(inv ? -a : a, y, x);
  y = fmaf(inv ? -b : b, x, y);
  x = fmaf(inv ? -a : a, y, x);
}
__device__ __forceinline__ void twiddle_fwd(uint32_t (&a)[4][4], float* d, const FftConst& k) {
#pragma unroll
  for (int q = 0; q < 4; q++)
#pragma unroll
    for (int j = 0; j < 2; j++) {
      float* x = d + 8 * q + 4 * j;
      rot(j, x[0], x[2], k.ta[2 * j], k.tb[2 * j]);
      rot(j, x[1], x[3], k.ta[2 * j + 1], k.tb[2 * j + 1]);
      a[q & 2][2 * j + (q & 1)] = pack2(x[0], x[1]);
      a[(q & 2) + 1][2 * j + (q & 1)] = pack2(x[2], x[3]);
    }
}
__device__ __forceinline__ void g_step(float* d, const uint32_t (&a)[4][4], uint32_t dre, uint32_t dim) {
  WgRS<32>::set<HI_SW64>(d, a[0], dre);
  WgRS<32>::set<HI_SW64>(d + 16, a[2], dre);
  WgRS<32>::mma<HI_SW64>(d, a[1], dim);
  WgRS<32>::mma<HI_SW64>(d + 16, a[3], dim);
  wg_commit();
}

__device__ __forceinline__ void conv_channel(const FftConst& k, uint32_t sb, int c, int wg, int w, int lane) {
  const uint32_t cb = sb + off_ch(c), bars = sb + OFF_BAR;
  const uint32_t du = desc_lo(cb, 1024), dg = desc_lo(sb + OFF_GT, 16), dz = desc_lo(cb + U_BYTES, 16);
  float U[32], H[32];
  uint32_t a[4][4], e[4][4];
  const float dv = __uint_as_float(lds32(sb + OFF_D + 4 * c));
  wg_fence();
  WgRS<64>::set<HI_SW32>(H, k.f[0], du + 256);
  WgRS<64>::mma<HI_SW32>(H, k.f[1], du + 256 + 32);
  wg_commit();
  wg_wait<0>();
  pin<32>(H);
  twiddle_fwd(a, H, k);
  if (ATT_GATE && H_EARLY) mbar_wait(bars + 8 * B_ATTN, 0);
  mbar_wait(bars + 8 * (B_U + (c < 3 ? c : 3)), 0);
  TSM(w == 0 && c < 3, 7 + wg);
  wg_fence();
  WgRS<64>::set<HI_SW32>(U, k.f[0], du);
  WgRS<64>::mma<HI_SW32>(U, k.f[1], du + 32);
  wg_commit();
  g_step(H, a, dg, dg + 64);
  wg_wait<1>();
  pin<32>(U);
  twiddle_fwd(e, U, k);
  wg_fence();
  g_step(U, e, dg, dg + 64);
  wg_wait<0>();
  pin<32>(U);
  pin<32>(H);
#pragma unroll
  for (int j = 0; j < 2; j++) {
    float pr[4][2], pi[4][2];
#pragma unroll
    for (int x = 0; x < 2; x++) {
      H[4 * j + x] += dv;
#pragma unroll
      for (int m = 0; m < 4; m++) {
#pragma unroll
        for (int q = 0; q <= m; q++) {
          const int ih = 16 * (q >> 1) + 2 * (q & 1) + 4 * j + x, iu = 16 * ((m - q) >> 1) + 2 * ((m - q) & 1) + 4 * j + x;
          pr[m][x] = q ? fmaf(H[ih], U[iu], pr[m][x]) : H[ih] * U[iu];
          pi[m][x] = q ? fmaf(H[ih], U[iu + 8], pi[m][x]) : H[ih] * U[iu + 8];
          pr[m][x] = fmaf(-H[ih + 8], U[iu + 8], pr[m][x]);
          pi[m][x] = fmaf(H[ih + 8], U[iu], pi[m][x]);
        }
      }
    }
#pragma unroll
    for (int m = 0; m < 4; m++) {
      a[m & 2][2 * j + (m & 1)] = pack2(pr[m][0], pr[m][1]);
      a[(m & 2) + 1][2 * j + (m & 1)] = pack2(pi[m][0], pi[m][1]);
    }
  }
  wg_fence();
  g_step(U, a, dg + 64, dg);
  const uint32_t za = cb + U_BYTES + (8 * w + (lane & 7)) * 128 + (((lane >> 3) ^ (lane & 7)) << 4);
  const uint32_t ya = cb + (lane >> 4) * 1024 + (8 * w + (lane & 7)) * 32 + ((((lane >> 3) ^ (lane >> 2)) & 1) << 4);
  wg_sync(1 + wg);
  wg_wait<0>();
  pin<32>(U);
  TSIF(w == 0, 80 + c);
#pragma unroll
  for (int p = 0; p < 2; p++) {
#pragma unroll
    for (int i = 0; i < 4; i++) {
      const int j = i & 1;
      float* x = U + 16 * p + 4 * j + (i & 2);
      rot(!j, x[8], x[0], k.ta[2 * j], k.tb[2 * j]);
      rot(!j, x[9], x[1], k.ta[2 * j + 1], k.tb[2 * j + 1]);
      e[p][i] = pack2(x[8], x[9]);
      e[2 + p][i] = pack2(x[0], x[1]);
    }
    stsm4(za ^ (64 * p), e[p]);
    stsm4((za ^ (64 * p)) + 4096, e[2 + p]);
  }
  fence_async_smem();
  wg_sync(1 + wg);
  wg_fence();
  WgRS<64>::set<HI_SW128>(H, k.fi[0], dz);
#pragma unroll
  for (int ks = 1; ks < 4; ks++) WgRS<64>::mma<HI_SW128>(H, k.fi[ks], dz + 128 * ks);
  wg_commit();
  wg_wait<0>();
  pin<32>(H);
  TSIF(w == 0, 88 + c);
#pragma unroll
  for (int j = 0; j < 8; j++)
    a[j >> 2][j & 3] = j < 2 ? pack2(H[4 * j], H[4 * j + 1]) : pack2(H[4 * j] + H[4 * j - 6], H[4 * j + 1] + H[4 * j - 5]);
  stsm4(ya, a[0]);
  stsm4(ya + 2048, a[1]);
  fence_async_smem();
  __syncwarp();
}

__device__ __forceinline__ void prep_slab(uint4* res, const uint2* sw, uint32_t sb, int slab, int w, int lane) {
  const int t = lane & 3, tp = (lane & 7) >> 1, pos = 8 * tp + 2 * (((lane >> 3) + tp) & 3) + (lane & 1);
  const uint32_t base = sb + OFF_KVS + slab * KVS_BYTES + pos * 128;
  uint32_t kk[2][4][4], vv[2][4];
  mbar_wait(sb + OFF_BAR + 8 * (B_KV + slab), 0);
#pragma unroll
  for (int h = 0; h < 2; h++) {
#pragma unroll
    for (int j = 0; j < 4; j++) {
      const uint32_t a = base + 128 * j;
      ldsm4t(kk[h][j], a + (((w + 4 * h) ^ ((a >> 7) & 7)) << 4));
    }
    const uint32_t a = base + KVS_V;
    ldsm4t(vv[h], a + (((w + 4 * h) ^ ((a >> 7) & 7)) << 4));
  }
#pragma unroll
  for (int h = 0; h < 2; h++) {
    uint32_t (&k)[4][4] = kk[h];
    uint32_t (&v)[4] = vv[h];
    const uint32_t w0 = __byte_perm(sw[h].x, 0, 0x1010), w1 = __byte_perm(sw[h].x, 0, 0x3232);
    const uint32_t w2 = __byte_perm(sw[h].y, 0, 0x1010), w3 = __byte_perm(sw[h].y, 0, 0x3232);
#pragma unroll
    for (int m = 0; m < 4; m++)
      v[m] = bmul(badd(badd(badd(bmul(k[0][m], w3), bmul(k[1][m], w2)), bmul(k[2][m], w1)), bmul(k[3][m], w0)), v[m]);
    uint32_t a[4];
#pragma unroll
    for (int m = 0; m < 4; m++) a[m] = (t & 1) ? v[(m + 3) & 3] : v[m];
    res[h] = (t & 2) ? make_uint4(a[2], a[3], a[0], a[1]) : make_uint4(a[0], a[1], a[2], a[3]);
  }
}

__device__ __forceinline__ void prep_gate(const Params& p, int b, int w, int lane) {
  uint2 gw[5], x[4][5];
#pragma unroll
  for (int j = 0; j < 5; j++) gw[j] = ldg64(reinterpret_cast<const uint2*>(p.gate_w) + lane + 32 * j);
#pragma unroll
  for (int i = 0; i < 4; i++)
#pragma unroll
    for (int j = 0; j < 5; j++)
      x[i][j] = ldg64(reinterpret_cast<const uint2*>(p.q) + (16 * b + 4 * w + i) * (DIM / 4) + lane + 32 * j);
  float s[4];
#pragma unroll
  for (int i = 0; i < 4; i++) {
    s[i] = 0.f;
#pragma unroll
    for (int j = 0; j < 5; j++) {
      const uint32_t m0 = bmul(x[i][j].x, gw[j].x), m1 = bmul(x[i][j].y, gw[j].y);
      s[i] += (bf_lo(m0) + bf_hi(m0)) + (bf_lo(m1) + bf_hi(m1));
    }
  }
  const bool h = lane & 16, q = lane & 8;
  const float a = (h ? s[2] : s[0]) + __shfl_xor_sync(0xffffffffu, h ? s[0] : s[2], 16);
  const float c = (h ? s[3] : s[1]) + __shfl_xor_sync(0xffffffffu, h ? s[1] : s[3], 16);
  float z = (q ? c : a) + __shfl_xor_sync(0xffffffffu, q ? a : c, 8);
#pragma unroll
  for (int o = 4; o > 0; o >>= 1) z += __shfl_xor_sync(0xffffffffu, z, o);
  z = bf_lo(pack2(z, 0.f));
  if ((lane & 7) == 0) g_gate[16 * b + 4 * w + (lane >> 3)] = bf_lo(pack2(__fdividef(1.f, 1.f + __expf(-z)), 0.f));
}

__device__ __forceinline__ uint32_t bmax(uint32_t a, uint32_t b) {
  uint32_t d;
  asm("max.bf16x2 %0, %1, %2;" : "=r"(d) : "r"(a), "r"(b));
  return d;
}
__device__ __forceinline__ void softmax_two(const float (&l)[2][2], uint32_t& p0, uint32_t& p1) {
  constexpr float kScale = 0.22360679774997896f, kLog2e = 1.4426950408889634f;
  const uint32_t r0 = pack2(l[0][0], l[1][0]), r1 = pack2(l[0][1], l[1][1]);
  const uint32_t x0 = pack2(bf_lo(r0) * kScale, bf_hi(r0) * kScale), x1 = pack2(bf_lo(r1) * kScale, bf_hi(r1) * kScale);
  uint32_t m = bmax(x0, x1);
  m = bmax(m, __shfl_xor_sync(0xffffffffu, m, 1));
  m = bmax(m, __shfl_xor_sync(0xffffffffu, m, 2));
  const float m0 = bf_lo(m) * kLog2e, m1 = bf_hi(m) * kLog2e;
  p0 = pack2(ex2(bf_lo(x0) * kLog2e - m0), ex2(bf_lo(x1) * kLog2e - m0));
  p1 = pack2(ex2(bf_hi(x0) * kLog2e - m1), ex2(bf_hi(x1) * kLog2e - m1));
}

__device__ __forceinline__ void halo_read(uint32_t (&kpv)[10], uint32_t (&vpv)[10], uint32_t (&tg)[7], const uint4* hp) {
#pragma unroll
  for (int j = 0; j < 7; j++) {
    uint32_t x0, x1, x2;
    asm volatile("ld.relaxed.gpu.global.v4.u32 {%0, %1, %2, %3}, [%4];"
                 : "=r"(x0), "=r"(x1), "=r"(x2), "=r"(tg[j]) : "l"(hp + 32 * j) : "memory");
    if (j < 4) kpv[3 * j] = x0; else vpv[3 * j - 10] = x0;
    if (j < 3) kpv[3 * j + 1] = x1; else vpv[3 * j - 9] = x1;
    if (j < 3) kpv[3 * j + 2] = x2; else if (j < 6) vpv[3 * j - 8] = x2;
  }
}

template <int ROT>
__device__ __forceinline__ void pack_qkv(const float* acc, uint32_t (&qlo)[10], uint32_t (&qhi)[10], uint32_t (&klo)[10],
                                         uint32_t (&khi)[10], uint32_t (&vlo)[10], uint32_t (&vhi)[10]) {
#pragma unroll
  for (int j = 0; j < 10; j++) {
    const int x = (j + ROT) % 10, tq = x < 8 ? x : 16 + x, tk = x < 8 ? 8 + x : 18 + x, tv = x < 8 ? 16 + x : 20 + x;
    khi[j] = pack2(acc[4 * tk + 2], acc[4 * tk + 3]);
    vhi[j] = movm(pack2(acc[4 * tv + 2], acc[4 * tv + 3]));
    qlo[j] = pack2(acc[4 * tq], acc[4 * tq + 1]);
    qhi[j] = pack2(acc[4 * tq + 2], acc[4 * tq + 3]);
    klo[j] = pack2(acc[4 * tk], acc[4 * tk + 1]);
    vlo[j] = pack2(acc[4 * tv], acc[4 * tv + 1]);
    asm volatile("" : "+r"(khi[j]), "+r"(qlo[j]), "+r"(qhi[j]), "+r"(klo[j]), "+r"(vlo[j]));
  }
}

template <int ROT> __device__ __forceinline__ void halo_send(const float* acc, uint4* ho, uint32_t tag) {
#pragma unroll
  for (int j = 0; j < 7; j++) {
    uint32_t x[3];
#pragma unroll
    for (int e = 0; e < 3; e++) {
      const int i = 3 * j + e, y = (i % 10 + ROT) % 10, tk = y < 8 ? 8 + y : 18 + y, tv = y < 8 ? 16 + y : 20 + y;
      x[e] = i < 10 ? pack2(acc[4 * tk + 2], acc[4 * tk + 3]) : i < 20 ? movm(pack2(acc[4 * tv + 2], acc[4 * tv + 3])) : 0u;
    }
    asm volatile("st.relaxed.gpu.global.v4.u32 [%0], {%1, %2, %3, %4};" ::"l"(ho + 32 * j), "r"(x[0]), "r"(x[1]), "r"(x[2]), "r"(tag) : "memory");
  }
}

__device__ __forceinline__ void attention(float* acc, uint32_t sb, int b, int par, int w, int lane, uint32_t tag) {
  const int g = lane >> 2, t = lane & 3;
  uint32_t klo[10], khi[10], vlo[10], vhi[10], qlo[10], qhi[10], kpv[10], vpv[10];
  if (HALO_FIRST && w == 3 && b < NCTA - 8) {
    uint4* ho = g_halo + (b * 2 + par) * 224 + lane;
    if (tail_first(b & 7)) halo_send<8>(acc, ho, tag);
    else halo_send<0>(acc, ho, tag);
    TSIF(par == 0, 76);
    pin<120>(acc);
  }
  if (tail_first(b & 7)) pack_qkv<8>(acc, qlo, qhi, klo, khi, vlo, vhi);
  else pack_qkv<0>(acc, qlo, qhi, klo, khi, vlo, vhi);
  const uint32_t xa = sb + OFF_KVX + (par * 3) * 2560 + lane * 16;
  if (w < 3) {
    sts128(xa + w * 2560, khi[0], khi[1], khi[2], khi[3]);
    sts128(xa + w * 2560 + 512, khi[4], khi[5], khi[6], khi[7]);
    sts128(xa + w * 2560 + 1024, khi[8], khi[9], vhi[0], vhi[1]);
    sts128(xa + w * 2560 + 1536, vhi[2], vhi[3], vhi[4], vhi[5]);
    sts128(xa + w * 2560 + 2048, vhi[6], vhi[7], vhi[8], vhi[9]);
  } else if (!HALO_FIRST && b < NCTA - 8) {
    uint4* ho = g_halo + (b * 2 + par) * 224 + lane;
#pragma unroll
    for (int j = 0; j < 7; j++) {
      const uint32_t x0 = j < 4 ? khi[3 * j] : vhi[3 * j - 10], x1 = j < 3 ? khi[3 * j + 1] : vhi[3 * j - 9];
      const uint32_t x2 = j < 3 ? khi[3 * j + 2] : j < 6 ? vhi[3 * j - 8] : 0u;
      asm volatile("st.relaxed.gpu.global.v4.u32 [%0], {%1, %2, %3, %4};" ::"l"(ho + 32 * j), "r"(x0), "r"(x1), "r"(x2), "r"(tag) : "memory");
    }
  }
  TSIF(par == 0 && w == 1, 64);
  TSIF(par == 0 && w == 3 && !HALO_FIRST, 76);
#pragma unroll
  for (int j = 0; j < 10; j++) vlo[j] = movm(vlo[j]);
  const bool far0 = 2 * t > g, far1 = 2 * t + 1 > g;
  const uint32_t mfar = (far0 ? 0x0000FFFFu : 0u) | (far1 ? 0xFFFF0000u : 0u);
  float slo[4][2], shi[4][2], lg[2][2];
  uint32_t phi[4], plo[4], qml[4], qmh[4];
#pragma unroll
  for (int h = 0; h < 4; h++) {
    const int f = h == 0 ? 0 : h == 1 ? 3 : h == 2 ? 5 : 8, hf = h < 2 ? 2 : 7;
    const bool mine = (h & 1) ? t >= 2 : t < 2;
    qml[h] = mine ? qlo[hf] : 0u;
    qmh[h] = mine ? qhi[hf] : 0u;
    float a[4] = {0.f, 0.f, 0.f, 0.f}, c[4] = {0.f, 0.f, 0.f, 0.f};
    mma16816(a, qlo[f], qhi[f], qlo[f + 1], qhi[f + 1], klo[f], klo[f + 1]);
    mma16816(c, qlo[f], qhi[f], qlo[f + 1], qhi[f + 1], khi[f], khi[f + 1]);
    mma1688(a, qml[h], qmh[h], klo[hf]);
    mma1688(c, qml[h], qmh[h], khi[hf]);
    slo[h][0] = a[0];
    slo[h][1] = a[1];
    shi[h][0] = lg[h & 1][0] = far0 ? a[2] : c[2];
    shi[h][1] = lg[h & 1][1] = far1 ? a[3] : c[3];
    if (!ATT_MERGE && (h & 1)) softmax_two(lg, phi[h - 1], phi[h]);
  }
  TSIF(par == 0 && w == 1, 65);
  wg_sync(1 + par);
  TSIF(par == 0 && w == 1, 66);
  const bool nohist = (w == 0) && (b < 8);
  const uint4* hp = g_halo + ((b - 8) * 2 + par) * 224 + lane;
  uint32_t tg[7];
  if (w > 0) {
    const uint4 v0 = lds128(xa + (w - 1) * 2560), v1 = lds128(xa + (w - 1) * 2560 + 512), v2 = lds128(xa + (w - 1) * 2560 + 1024);
    const uint4 v3 = lds128(xa + (w - 1) * 2560 + 1536), v4 = lds128(xa + (w - 1) * 2560 + 2048);
    kpv[0] = v0.x; kpv[1] = v0.y; kpv[2] = v0.z; kpv[3] = v0.w; kpv[4] = v1.x; kpv[5] = v1.y; kpv[6] = v1.z; kpv[7] = v1.w;
    kpv[8] = v2.x; kpv[9] = v2.y; vpv[0] = v2.z; vpv[1] = v2.w; vpv[2] = v3.x; vpv[3] = v3.y; vpv[4] = v3.z; vpv[5] = v3.w;
    vpv[6] = v4.x; vpv[7] = v4.y; vpv[8] = v4.z; vpv[9] = v4.w;
  } else if (nohist) {
#pragma unroll
    for (int j = 0; j < 10; j++) kpv[j] = vpv[j] = 0u;
  } else {
    TSIF(par == 0, 77);
    halo_read(kpv, vpv, tg, hp);
  }
  if (w == 0 && !nohist) {
    int spins = 0;
    while (true) {
      bool ok = true;
#pragma unroll
      for (int j = 0; j < 7; j++) ok = ok && tg[j] == tag;
      if (__all_sync(0xffffffffu, ok) || ++spins > SPIN_LIMIT) break;
      halo_read(kpv, vpv, tg, hp);
    }
    TSIF(par == 0, 79);
  }
#pragma unroll
  for (int h = 0; h < 4; h++) {
    const int f = h == 0 ? 0 : h == 1 ? 3 : h == 2 ? 5 : 8, hf = h < 2 ? 2 : 7;
    float a[4] = {0.f, 0.f, 0.f, 0.f};
    mma16816(a, qlo[f], qhi[f], qlo[f + 1], qhi[f + 1], kpv[f], kpv[f + 1]);
    mma1688(a, qml[h], qmh[h], kpv[hf]);
    const float ninf = __int_as_float(0xff800000);
    lg[h & 1][0] = far0 ? (nohist ? ninf : a[0]) : slo[h][0];
    lg[h & 1][1] = far1 ? (nohist ? ninf : a[1]) : slo[h][1];
    if (h & 1) {
      softmax_two(lg, plo[h - 1], plo[h]);
      if (ATT_MERGE) {
        const float lh[2][2] = {{shi[h - 1][0], shi[h - 1][1]}, {shi[h][0], shi[h][1]}};
        softmax_two(lh, phi[h - 1], phi[h]);
      }
    }
  }
  TSIF(par == 0 && w <= 1, 67 + w);
  uint32_t ov[20];
#pragma unroll
  for (int hp = 0; hp < 2; hp++) {
    const int hf = hp ? 7 : 2;
    float sh[4] = {0.f, 0.f, 0.f, 0.f}, i0 = 0.f, i1 = 0.f;
#pragma unroll
    for (int e = 0; e < 2; e++) {
      const int h = 2 * hp + e, f = h == 0 ? 0 : h == 1 ? 3 : h == 2 ? 5 : 8;
      const uint32_t a0 = plo[h] & mfar, a2 = plo[h] & ~mfar, a3 = phi[h] & mfar, c1 = phi[h] & ~mfar;
      float sum[4] = {0.f, 0.f, 0.f, 0.f};
      mma1688(sum, plo[h], phi[h], 0x3F803F80u);
      const float r0 = rcp(sum[0]), r1 = rcp(sum[2]);
#pragma unroll
      for (int j = f; j < f + 2; j++) {
        float o[4] = {0.f, 0.f, 0.f, 0.f};
        mma16816(o, a0, 0u, a2, a3, vpv[j], vlo[j]);
        mma1688(o, 0u, c1, vhi[j]);
        ov[2 * j] = pack2(o[0] * r0, o[1] * r0);
        ov[2 * j + 1] = pack2(o[2] * r1, o[3] * r1);
      }
      const bool mine = e ? g >= 4 : g < 4;
      mma16816(sh, a0, 0u, a2, a3, mine ? vpv[hf] : 0u, mine ? vlo[hf] : 0u);
      mma1688(sh, 0u, c1, mine ? vhi[hf] : 0u);
      if (e == 0 || t >= 2) {
        i0 = r0;
        i1 = r1;
      }
    }
    ov[2 * hf] = pack2(sh[0] * i0, sh[1] * i0);
    ov[2 * hf + 1] = pack2(sh[2] * i1, sh[3] * i1);
  }
  TS(32 + 4 * par + w);
  mbar_wait(sb + OFF_BAR + 8 * B_P1, 0);
  const uint32_t oa = sb + OFF_OA + (lane >> 4) * 2048 + (32 * w + 2 * (lane & 15) + par) * 16;
#pragma unroll
  for (int j = 0; j < 5; j++) stsm4(oa + 4096 * j, ov + 4 * j);
  TSIF(par == 0 && w == 0, 120);
  fence_async_smem();
  TSIF(par == 0 && w == 0, 121);
  __syncwarp();
  if (lane == 0) mbar_arrive(sb + OFF_BAR + 8 * B_ATTN);
  TSM(w == 0 || w == 2, 122 + par + (w == 2 ? 3 : 0));
}

struct Maps {
  CUtensorMap x, wm, wt, k, v, y, wo, qm, qt, om, ot, u;
};

__device__ __forceinline__ void load_stage(uint32_t sb, int kb, int b, const Maps& m) {
  const uint32_t st = sb + (kb & 3) * STAGE_BYTES, bar = sb + OFF_BAR + 8 * (B_FULL1 + (kb & 3));
  const int r = b >> 3, hg = b & 7, slab = kb - KV_KB;
  const bool kv = slab >= 0 && slab < 5;
  const uint32_t kbar = sb + OFF_BAR + 8 * (B_KV + slab), dst = sb + OFF_KVS + slab * KVS_BYTES;
  mbar_expect_tx(bar, STAGE_BYTES);
  if (kv) mbar_expect_tx(kbar, KVS_BYTES);
  tma_3d(st, &m.x, 64 * kb, 64 * r, 0, bar);
  if (kv && KV_MIX) tma_3d(dst, &m.k, 0, 32 * (b >> 1) - 3, 2 * slab + (b & 1), kbar);
  tma_3d(st + ST_W, &m.wm, 80 * hg + (tail_first(hg) ? 16 : 0), 64 * kb, 0, bar);
  if (kv && KV_MIX) tma_3d(dst + KVS_V, &m.v, 0, 32 * (b >> 1), 2 * slab + (b & 1), kbar);
  tma_3d(st + ST_WT, &m.wt, 80 * hg + (tail_first(hg) ? 0 : 64), 64 * kb, 0, bar);
  if (kv && !KV_MIX) tma_3d(dst, &m.k, 0, 32 * (b >> 1) - 3, 2 * slab + (b & 1), kbar);
  if (kv && !KV_MIX) tma_3d(dst + KVS_V, &m.v, 0, 32 * (b >> 1), 2 * slab + (b & 1), kbar);
}

__global__ void __launch_bounds__(NTHR, 1) fused_kernel(const __grid_constant__ Maps m, const Params p) {
  extern __shared__ __align__(1024) uint8_t smem[];
  const uint32_t sb = (uint32_t)__cvta_generic_to_shared(smem);
  const uint32_t bars = sb + OFF_BAR;
  const int tid = threadIdx.x, lane = tid & 31;
  int b = blockIdx.x;
  if (BMAP == 1) b = (((b & 63) >> 3) * 2 + (b & 1)) * 8 + (((b < 64 ? 0x6521 : 0x7430) >> (4 * ((b >> 1) & 3))) & 7);
  if (BMAP == 2) b = ((b & 63) >> 2) * 8 + (((b < 64 ? 0x6521 : 0x7430) >> (4 * (b & 3))) & 7);
  if (BMAP == 3) b = (((b & 63) >> 3) * 2 + (b & 1)) * 8 + (((b < 64 ? 0x7430 : 0x6521) >> (4 * ((b >> 1) & 3))) & 7);
  if (BMAP == 4) b = (((b >> 4) * 2 + (b & 1)) * 8) + ((b >> 1) & 7);
  if (BMAP == 5) b = 127 - b;
  const int r = b >> 3, hg = b & 7, pre = blockIdx.x < 64 ? PRE2 : PRE2G;

  if (tid == T_ISSUE) {
    TSM(true, 0);
#pragma unroll
    for (int i = 0; i < 4; i++) mbar_init(bars + 8 * (B_FULL1 + i), 1);
#pragma unroll
    for (int i = 0; i < 3; i++) mbar_init(bars + 8 * (B_KV + i), 1);
    fence_async_smem();
#pragma unroll 1
    for (int kb = 0; kb <= pre; kb++) load_stage(sb, kb, b, m);
  } else if (tid >= T_PF && tid < T_PF + 12) {
    tm_prefetch(&m.x + (tid - T_PF));
  } else if (tid == T_INIT) {
#pragma unroll
    for (int i = 0; i < 4; i++) mbar_init(bars + 8 * (B_EMPTY1 + i), 8);
#pragma unroll
    for (int i = 0; i < 8; i++) mbar_init(bars + 8 * (B_FULL2 + i), 1);
#pragma unroll
    for (int i = 0; i < 4; i++) mbar_init(bars + 8 * (B_EMPTY2 + i), 8);
#pragma unroll
    for (int i = 0; i < 4; i++) mbar_init(bars + 8 * (B_U + i), 1);
    mbar_init(bars + 8 * B_HA, 4);
    mbar_init(bars + 8 * B_GATE, 4);
    mbar_init(bars + 8 * B_HB, 1);
    mbar_init(bars + 8 * B_KVD, 4);
    mbar_init(bars + 8 * B_QF, 1);
    mbar_init(bars + 8 * B_ATTN, 8);
    mbar_init(bars + 8 * B_P1, 8);
    mbar_init(bars + 8 * B_C34, 1);
#pragma unroll
    for (int i = 0; i < 5; i++) mbar_init(bars + 8 * (B_YST + i), 4);
#pragma unroll
    for (int i = 0; i < 5; i++) mbar_init(bars + 8 * (B_US + i), 4);
    mbar_init(bars + 8 * B_YSIG, 1);
    mbar_init(bars + 8 * B_YFULL, 1);
    mbar_init(bars + 8 * B_EPOCH, 1);
    mbar_init(bars + 8 * B_PREP, 4);
    mbar_init(bars + 8 * B_USIG, 1);
    mbar_init(bars + 8 * B_WST, 1);
#pragma unroll
    for (int i = 3; i < 5; i++) mbar_init(bars + 8 * (B_KV + i), 1);
    mbar_init(bars + 8 * B_E3, 8);
    mbar_init(bars + 8 * B_LAST, 1);
    mbar_init(bars + 8 * B_OSIG, 1);
    mbar_init(bars + 8 * B_WOP, 1);
    fence_async_smem();
  }
  const int warp = __shfl_sync(0xffffffffu, tid >> 5, 0), wg = warp >> 2, w = warp & 3;
  __syncthreads();

  if (wg == 3) {
    asm volatile("setmaxnreg.dec.sync.aligned.u32 56;");
    if (w == 0) {
      if (lane == 0) {
#pragma unroll 1
        for (int kb = 1 + pre; kb < 10; kb++) {
          if (GOOD_WAIT && !(blockIdx.x < 64) && kb == GOOD_WAIT) mbar_wait(bars + 8 * B_FULL1, 0);
          if (kb >= 4) mbar_wait(bars + 8 * (kb == 7 ? B_E3 : B_EMPTY1 + (kb & 3)), (kb >> 3) & 1);
          TSIF(kb >= 4, 44 + kb);
          load_stage(sb, kb, b, m);
          TSIF(kb == 3, 60);
          if (kb == TRIG_KB) mbar_arrive(bars + 8 * B_LAST);
        }
        mbar_wait(bars + 8 * B_WOP, 0);
        mbar_wait(bars + 8 * WL_TRIG, 0);
        mbar_wait(bars + 8 * B_EPOCH, 0);
        flag_wait(g_cnt + C_W + 32 * hg, (lds32(sb + OFF_EPOCH) + 1) * 16);
        TS(30);
#pragma unroll 1
        for (int j = 0; j < 8; j++) {
          if (j >= 6) mbar_wait(bars + 8 * (B_EMPTY2 + j - 6), 0);
          if (j == 4) mbar_wait(bars + 8 * B_ATTN, 0);
          TSIF(j >= 6, 100 + j);
          if (RF_GATE && j == 6) mbar_wait(bars + 8 * B_YSIG, 0);
          mbar_expect_tx(bars + 8 * (B_FULL2 + j), j == 0 ? WO_BYTES : j == 5 ? O_BYTES + WO_BYTES + 512 : O_BYTES + WO_BYTES);
          bulk_load(sb + off_w(j), g_WO + (hg * 8 + step_src(hg, j)) * 800, WO_BYTES, bars + 8 * (B_FULL2 + j));
        }
        mbar_wait(bars + 8 * (B_EMPTY2 + 3), 0);
        mbar_expect_tx(bars + 8 * B_QF, O_BYTES);
        tma_2d(sb + OFF_QS, &m.qm, 80 * hg, 128 * r, bars + 8 * B_QF);
        tma_2d(sb + OFF_QT, &m.qt, 80 * hg + 64, 128 * r, bars + 8 * B_QF);
      }
    } else if (w == 1) {
      unsigned epoch = 0;
      if (lane == 0) {
        epoch = atomicAdd(g_cnt + C_LAUNCH, 1u) / NCTA;
        asm volatile("st.shared.u32 [%0], %1;" ::"r"(sb + OFF_EPOCH), "r"(epoch) : "memory");
        mbar_arrive(bars + 8 * B_EPOCH);
        mbar_wait(bars + 8 * B_KVD, 0);
        mbar_expect_tx(bars + 8 * B_HB, 5 * 4096);
#pragma unroll 1
        for (int c = 0; c < 5; c++) {
          if (c == 3) mbar_wait(bars + 8 * B_S3, 0);
          bulk_load(sb + off_ch(c) + U_BYTES, p.ssm_k + (5 * b + c) * SEQ, 4096, bars + 8 * B_HB);
        }
#pragma unroll
        for (int c = 0; c < 4; c++) mbar_expect_tx(bars + 8 * (B_U + c), c < 3 ? U_BYTES : 2 * U_BYTES);
        const uint4* usrc = g_U + 5 * b * U_PITCH;
        mbar_wait(bars + 8 * B_USIG, 0);
        flag_wait(g_cnt + C_PREP + 32 * (b & 15), (epoch + 1) * NCTA);
        TS(23);
#pragma unroll
        for (int c = 0; c < 5; c++) {
          if (c == 3) mbar_wait(bars + 8 * (B_U + 2), 0);
          bulk_load(sb + off_ch(c), usrc + c * U_PITCH, U_BYTES, bars + 8 * (B_U + (c < 3 ? c : 3)));
          TSIF(c == 0 || c == 4, 116 + (c >> 2));
        }
      }
      epoch = __shfl_sync(0xffffffffu, epoch, 0);
      if (lane < 8) {
        const int src = (b & ~7) | step_src(hg, lane);
        mbar_wait(bars + 8 * B_OSIG, 0);
        TS(20);
        flag_wait(g_cnt + C_O + 32 * src, epoch + 1);
        if (lane >= 1 && lane < 4) bulk_load(sb + off_o(lane), g_O + src * 1280, O_BYTES, bars + 8 * (B_FULL2 + lane));
        __syncwarp(0xff);
        TS(21);
        if (lane == 5) bulk_load(sb + OFF_GATE, g_gate + 128 * r, 512, bars + 8 * (B_FULL2 + 5));
#pragma unroll 1
        for (int j = 4; j < 8; j++) {
          if (lane == j) {
            mbar_wait(bars + 8 * (j < 6 ? B_C34 : B_EMPTY2 + j - 6), 0);
            if (RF_GATE && j == 6) mbar_wait(bars + 8 * B_YSIG, 0);
            bulk_load(sb + off_o(j), g_O + src * 1280, O_BYTES, bars + 8 * (B_FULL2 + j));
          }
          __syncwarp(0xff);
        }
        TS(22);
      }
    } else if (w == 2) {
      mbar_wait(bars + 8 * B_PREP, 0);
      flag_signal(g_cnt + C_PREP, 16, lane);
      TS(25);
      if (lane == 0) mbar_arrive(bars + 8 * B_USIG);
      mbar_wait(bars + 8 * B_GATE, 0);
      if ((NOMB & 1) && lane == 0) asm volatile("fence.release.gpu;" ::: "memory");
      mbar_wait(bars + 8 * B_ATTN, 0);
      if (lane == 0) {
        if (O_DEFER) mbar_wait(bars + 8 * (B_U + 3), 0);
        asm volatile("cp.async.bulk.global.shared::cta.bulk_group [%0], [%1], 20480;\ncp.async.bulk.commit_group;\n"
                     "cp.async.bulk.wait_group 0;\nfence.proxy.async.global;" ::"l"(g_O + b * 1280), "r"(sb + OFF_OA) : "memory");
      }
      TS(74);
      if (!(NOMB & 1)) flag_signal(g_cnt + C_O + 32 * b, 1, lane);
      else if (lane == 0) flag_bump(g_cnt + C_O + 32 * b);
      TS(26);
      if (lane == 0) mbar_arrive(bars + 8 * B_OSIG);

    } else {
      if (lane == 0) {
        uint4* dst = g_WO + (hg * 8 + (r >> 1)) * 800 + (r & 1) * 80;
        mbar_wait(bars + 8 * B_P1, 0);
        mbar_wait(bars + 8 * WB_TRIG, 0);
        mbar_expect_tx(bars + 8 * B_WST, WO_BYTES / 2);
        tma_3d(sb + OFF_WS, &m.wo, 0, 40 * r, 5 * hg, bars + 8 * B_WST);
        mbar_wait(bars + 8 * B_WST, 0);
        mbar_wait(bars + 8 * WO_TRIG, 0);
#pragma unroll 1
        for (int n = 0; n < 5; n++)
          asm volatile("cp.async.bulk.global.shared::cta.bulk_group [%0], [%1], 1280;" ::"l"(dst + 160 * n), "r"(sb + OFF_WS + 1280 * n) : "memory");
        asm volatile("cp.async.bulk.commit_group;\ncp.async.bulk.wait_group 0;\nfence.proxy.async.global;" ::: "memory");
        if (!(NOMB & 4)) asm volatile("fence.release.gpu;" ::: "memory");
        flag_bump(g_cnt + C_W + 32 * hg);
        mbar_arrive(bars + 8 * B_WOP);
        TS(71);
#pragma unroll 1
        for (int c = 0; c < 5; c++) {
          mbar_wait(bars + 8 * (B_YST + c), 0);
          asm volatile("cp.async.bulk.global.shared::cta.bulk_group [%0], [%1], 4096;\ncp.async.bulk.commit_group;"
                       ::"l"(g_Y + (5 * b + c) * Y_PITCH), "r"(sb + off_ch(c)) : "memory");
          if (c == 2) {
            asm volatile("cp.async.bulk.wait_group.read 0;" ::: "memory");
            mbar_arrive(bars + 8 * B_C34);
          }
        }
        asm volatile("cp.async.bulk.wait_group 0;\nfence.proxy.async.global;" ::: "memory");
        TS(75);
        if (!(NOMB & 2)) asm volatile("fence.release.gpu;" ::: "memory");
        flag_bump(g_cnt + C_Y + 32 * (b >> 4));
        TS(27);
        mbar_arrive(bars + 8 * B_YSIG);
        mbar_expect_tx(bars + 8 * B_YFULL, 20480);
        flag_wait(g_cnt + C_Y + 32 * hg, (lds32(sb + OFF_EPOCH) + 1) * 16);
        TS(24);
        tma_2d(sb + OFF_YT, &m.y, 128 * r, 80 * hg, bars + 8 * B_YFULL);
        tma_2d(sb + OFF_YT + 10240, &m.y, 128 * r + 64, 80 * hg, bars + 8 * B_YFULL);
      }
    }
  } else {
    asm volatile("setmaxnreg.inc.sync.aligned.u32 152;");
    if (wg < 2) {
      float acc[120];
#pragma unroll
      for (int i = 0; i < 120; i++) acc[i] = 0.f;
      const uint32_t da = desc_lo(sb + wg * 8192, 16), db = desc_lo(sb + ST_W, 8192), dc = desc_lo(sb + ST_WT, 2048);
      if (PW1) pin<120>(acc);
      if (PW1 == 2) mbar_wait(bars + 8 * B_FULL1, 0);
#pragma unroll 1
      for (int kb = 0; kb < 10; kb++) {
        mbar_wait(bars + 8 * (B_FULL1 + (kb & 3)), (kb >> 2) & 1);
        const uint32_t so = (kb & 3) * (STAGE_BYTES >> 4);
        wg_fence();
#pragma unroll
        for (int k = 0; k < 4; k++) {
          WgSST<192>::mma<HI_SW128, HI_SW128>(acc, da + so + 2 * k, db + so + 128 * k, 1);
          WgSST<48>::mma<HI_SW128, HI_SW32>(acc + 96, da + so + 2 * k, dc + so + 32 * k, 1);
        }
        wg_commit();
        wg_wait<1>();
        if (kb > 0 && lane == 0) mbar_arrive(bars + 8 * (kb == 4 ? B_E3 : B_EMPTY1 + ((kb - 1) & 3)));
      }
      mbar_wait(bars + 8 * B_EPOCH, 0);
      const uint32_t tag = lds32(sb + OFF_EPOCH) + 1;
      mbar_wait(bars + 8 * B_S3, 0);
      wg_wait<0>();
      pin<120>(acc);
      if (lane == 0) mbar_arrive(bars + 8 * B_P1);
      TSM(w == 0, 3 + wg);
      attention(acc, sb, b, wg, w, lane, tag);
    } else {
      const int tw = tid & 127, chl = 64 * (b & 1) + 8 * w + (lane >> 2);
      uint4* up = g_U + chl * U_PITCH + ((4 * (b >> 1) + (lane & 3)) ^ ((b >> 2) & 1));
      uint2 sw[10];
      uint32_t dv = 0;
      if (lane < 5) dv = __ldg(reinterpret_cast<const unsigned short*>(p.ssm_D) + 5 * b + lane);
#pragma unroll
      for (int i = 0; i < 10; i++) sw[i] = ldg64(reinterpret_cast<const uint2*>(p.shift_k) + chl + 128 * (i >> 1) + 32 * (i & 1));
      uint32_t tab[12];
      float tt[4];
      fft_tables(tab, tw);
      fft_twiddles(tt, tw);
      uint4 res[10];
#pragma unroll
      for (int i = 0; i < 10; i++) res[i] = make_uint4(0, 0, 0, 0);
#pragma unroll 1
      for (int slab = 0; slab < 5; slab++) {
#pragma unroll
        for (int i = 0; i < 8; i++) res[i] = res[i + 2];
        prep_slab(res + 8, sw, sb, slab, w, lane);
        TSIF(w == 0, 99 + 4 * slab);
#pragma unroll
        for (int i = 0; i < 8; i++) sw[i] = sw[i + 2];
      }
      TSIF(w == 0, 28);
      __syncwarp();
      if (lane == 0) mbar_arrive(bars + 8 * B_KVD + ((res[8].x ^ res[9].x) & p.zero));
      mbar_wait(bars + 8 * B_KVD, 0);
      fft_tables_store(tab, sb, tw);
      mbar_wait(bars + 8 * B_LAST, 0);
#pragma unroll
      for (int i = 0; i < 10; i++) up[(128 * (i >> 1) + 32 * (i & 1)) * U_PITCH] = res[i];
      __syncwarp();
      if (lane == 0) mbar_arrive(bars + 8 * B_PREP);
      TSIF(w == 0 && !U_TMA, 5);
      mbar_wait(bars + 8 * (G_AFTER ? B_USIG : B_LAST), 0);
      prep_gate(p, b, w, lane);
      __syncwarp();
      if (lane == 0) mbar_arrive(bars + 8 * B_GATE);
      TSIF(w == 0, 72);
      mbar_wait(bars + 8 * B_HB, 0);
      TSIF(w == 0, 2);
      const uint32_t ha = sb + U_BYTES + ((tw >> 3) * 16 + 8 + (tw & 7)) * 16;
      uint4 hv[5];
#pragma unroll
      for (int c = 0; c < 5; c++) hv[c] = lds128(ha + off_ch(c));
      __syncwarp();
#pragma unroll
      for (int c = 0; c < 5; c++) sts128((ha ^ 16) + off_ch(c), hv[c].x, hv[c].y, hv[c].z, hv[c].w);
      sts128(sb + OFF_TT + 16 * tw, __float_as_uint(tt[0]), __float_as_uint(tt[1]), __float_as_uint(tt[2]), __float_as_uint(tt[3]));
      if (tw < 5) asm volatile("st.shared.f32 [%0], %1;" ::"r"(sb + OFF_D + 4 * tw), "f"(bf_lo(dv) * 0.125f) : "memory");
      fence_async_smem();
      __syncwarp();
      if (lane == 0) mbar_arrive(bars + 8 * B_HA);
      TSIF(w == 0, 6);
    }

    FftConst fc;
    TSM(w == 0 && wg == 0, 104);
    mbar_wait(bars + 8 * B_HA, 0);
    fft_matrices(fc, sb, w, lane);
    TSM(w == 0 && wg == 0, 105);
    if (ATT_GATE && !H_EARLY) mbar_wait(bars + 8 * B_ATTN, 0);
    TSM(w == 0 && wg == 2, 124);
#pragma unroll 1
    for (uint32_t tasks = wg == 0 ? TASK0 : wg == 1 ? TASK1 : TASK2; tasks; tasks >>= 4) {
      const int c = (tasks & 7) - 1;
      conv_channel(fc, sb, c, wg, w, lane);
      if (lane == 0) mbar_arrive(bars + 8 * (B_YST + c));
      TSM(w == 0, 10 + c);
    }

    if (wg < 2) {
      const int g = lane >> 2;
      float acc[40];
#pragma unroll
      for (int i = 0; i < 40; i++) acc[i] = 0.f;
      const uint32_t da = desc_lo(sb + wg * 1024, 2048), db = desc_lo(sb, 2560);
      mbar_wait(bars + 8 * B_ATTN, 0);
      mbar_wait(bars + 8 * (B_YST + 3), 0);
      if (WO_GATE == 1) mbar_wait(bars + 8 * (B_YST + 4), 0);
      if (PW2) mbar_wait(bars + 8 * B_FULL2, 0);
      TSM(w == 0, 15 + wg);
#pragma unroll 1
      for (int j = 0; j < 8; j++) {
        mbar_wait(bars + 8 * (B_FULL2 + j), 0);
        const uint32_t oa = da + (off_o(j) >> 4), ob = db + (off_w(j) >> 4);
        wg_fence();
#pragma unroll
        for (int k = 0; k < 5; k++) WgSST<80>::mma<HI_NONE, HI_SW32>(acc, oa + 256 * k, ob + 32 * k, 1);
        wg_commit();
        wg_wait<1>();
        if (j >= 1 && j <= 4 && lane == 0) mbar_arrive(bars + 8 * (B_EMPTY2 + j - 1));
      }
      TSIF(w == 0 && wg == 0, 113);
      const int tr = 64 * wg + 16 * w + (lane & 15);
      const uint32_t fm = sb + OFF_QS + tr * 128, fx = (lane >> 4) ^ (tr & 7);
      const uint32_t ft = sb + OFF_QT + tr * 32 + (((lane >> 4) ^ (tr >> 2)) & 1) * 16;
      const float g0 = __uint_as_float(lds32(sb + OFF_GATE + (64 * wg + 16 * w + g) * 4));
      const float g1 = __uint_as_float(lds32(sb + OFF_GATE + (64 * wg + 16 * w + 8 + g) * 4));
      const uint32_t ga = pack2(g0, g0), gb = pack2(g1, g1);
      const uint32_t na = pack2(1.f - g0, 1.f - g0), nb = pack2(1.f - g1, 1.f - g1);

      wg_wait<0>();
      pin<40>(acc);
      TSM(w == 0, 17 + wg);
      uint32_t pb[20];
#pragma unroll
      for (int j = 0; j < 10; j++) {
        pb[2 * j] = bmul(na, pack2(acc[4 * j], acc[4 * j + 1]));
        pb[2 * j + 1] = bmul(nb, pack2(acc[4 * j + 2], acc[4 * j + 3]));
        asm volatile("" : "+r"(pb[2 * j]), "+r"(pb[2 * j + 1]));
      }
      const uint32_t ya = sb + OFF_YT + wg * 10240 + ((lane >> 4) * 8 + (lane & 7)) * 128 +
                          (((2 * w + (((lane >> 3) & 1) ^ wg)) ^ (lane & 7)) << 4);
      uint32_t qf[20];
      mbar_wait(bars + 8 * B_QF, 0);
#pragma unroll
      for (int j = 0; j < 5; j++) ldsm4(qf + 4 * j, j < 4 ? fm + ((fx ^ (2 * j)) << 4) : ft);
      mbar_wait(bars + 8 * B_YFULL, 0);
      TSM(w == 0 && wg == 0, 19);
#pragma unroll
      for (int j = 0; j < 5; j++) {
        uint32_t y[4];
        ldsm4t(y, ya + 2048 * j);
#pragma unroll
        for (int i = 0; i < 4; i++) qf[4 * j + i] = badd(bmul((i & 1) ? gb : ga, bmul(qf[4 * j + i], y[i])), pb[4 * j + i]);
      }
#pragma unroll
      for (int j = 0; j < 5; j++) stsm4(j < 4 ? fm + ((fx ^ (2 * j)) << 4) : ft, qf + 4 * j);
      fence_async_smem();
      __syncwarp();
      if (lane == 0) {
        const int row = 64 * wg + 16 * w;
        asm volatile("cp.async.bulk.tensor.2d.global.shared::cta.bulk_group [%0, {%2, %3}], [%1];"
                     ::"l"(&m.om), "r"(sb + OFF_QS + row * 128), "r"(80 * hg), "r"(128 * r + row) : "memory");
        asm volatile("cp.async.bulk.tensor.2d.global.shared::cta.bulk_group [%0, {%2, %3}], [%1];"
                     ::"l"(&m.ot), "r"(sb + OFF_QT + row * 32), "r"(80 * hg + 64), "r"(128 * r + row) : "memory");
        asm volatile("cp.async.bulk.commit_group;\ncp.async.bulk.wait_group.read 0;" ::: "memory");
      }
      TSM(true, 40 + 4 * wg + w);
      if (ENDBAR) asm volatile("bar.sync 15, 256;" ::: "memory");
    }
  }
}

typedef CUresult (*EncodeFn)(CUtensorMap*, CUtensorMapDataType, cuuint32_t, void*, const cuuint64_t*, const cuuint64_t*,
                             const cuuint32_t*, const cuuint32_t*, CUtensorMapInterleave, CUtensorMapSwizzle,
                             CUtensorMapL2promotion, CUtensorMapFloatOOBfill);

void encode(EncodeFn fn, CUtensorMap* tm, const void* base, int rank, const cuuint64_t* dims, const cuuint64_t* strides,
            const cuuint32_t* box, CUtensorMapSwizzle swz) {
  const cuuint32_t ones[3] = {1, 1, 1};
  fn(tm, CU_TENSOR_MAP_DATA_TYPE_BFLOAT16, rank, const_cast<void*>(base), dims, strides, box, ones,
     CU_TENSOR_MAP_INTERLEAVE_NONE, swz, CU_TENSOR_MAP_L2_PROMOTION_L2_128B, CU_TENSOR_MAP_FLOAT_OOB_FILL_NONE);
}

}

extern "C" void kernel_launch(void* const* d_in, const int* in_sizes, int n_in, void* d_out, int out_size) {
  (void)in_sizes; (void)n_in; (void)out_size;
  Params p;
  p.q = (const __nv_bfloat16*)d_in[0];
  p.k = (const __nv_bfloat16*)d_in[1];
  p.v = (const __nv_bfloat16*)d_in[2];
  p.shift_k = (const __nv_bfloat16*)d_in[3];
  p.ssm_k = (const __nv_bfloat16*)d_in[4];
  p.ssm_D = (const __nv_bfloat16*)d_in[5];
  p.wqkv = (const __nv_bfloat16*)d_in[7];
  p.wo = (const __nv_bfloat16*)d_in[8];
  p.gate_w = (const __nv_bfloat16*)d_in[9];
  p.out = (__nv_bfloat16*)d_out;
  p.zero = 0;

  static EncodeFn fn = nullptr;
  static void *yaddr = nullptr, *uaddr = nullptr;
  if (!fn) {
    cudaDriverEntryPointQueryResult qr;
    void* f = nullptr;
    cudaGetDriverEntryPoint("cuTensorMapEncodeTiled", &f, cudaEnableDefault, &qr);
    fn = (EncodeFn)f;
    cudaGetSymbolAddress(&yaddr, g_Y);
    cudaGetSymbolAddress(&uaddr, g_U);
    cudaFuncSetAttribute(fused_kernel, cudaFuncAttributeMaxDynamicSharedMemorySize, SMEM_BYTES);
  }
  Maps m;
  {
    const cuuint64_t dims[3] = {640, 1024, 2}, st[2] = {2560, 1280};
    const cuuint32_t box[3] = {64, 64, 2};
    encode(fn, &m.x, p.q, 3, dims, st, box, CU_TENSOR_MAP_SWIZZLE_128B);
  }
  {
    const cuuint64_t dims[3] = {640, 640, 3}, st[2] = {3840, 1280};
    const cuuint32_t box[3] = {64, 64, 3}, boxt[3] = {16, 64, 3};
    encode(fn, &m.wm, p.wqkv, 3, dims, st, box, CU_TENSOR_MAP_SWIZZLE_128B);
    encode(fn, &m.wt, p.wqkv, 3, dims, st, boxt, CU_TENSOR_MAP_SWIZZLE_32B);
  }
  {
    const cuuint64_t dims[3] = {64, 2048, 10}, st[2] = {1280, 128};
    const cuuint32_t boxk[3] = {64, 35, 1}, boxv[3] = {64, 32, 1};
    encode(fn, &m.k, p.k, 3, dims, st, boxk, CU_TENSOR_MAP_SWIZZLE_128B);
    encode(fn, &m.v, p.v, 3, dims, st, boxv, CU_TENSOR_MAP_SWIZZLE_128B);
  }
  {
    const cuuint64_t dims[3] = {16, 640, 40}, st[2] = {1280, 32};
    const cuuint32_t box[3] = {16, 40, 5};
    encode(fn, &m.wo, p.wo, 3, dims, st, box, CU_TENSOR_MAP_SWIZZLE_32B);
  }
  {
    const cuuint64_t dims[2] = {2048, 640}, st[1] = {Y_PITCH * 16};
    const cuuint32_t box[2] = {64, 80};
    encode(fn, &m.y, yaddr, 2, dims, st, box, CU_TENSOR_MAP_SWIZZLE_128B);
    const cuuint64_t stu[1] = {U_PITCH * 16};
    const cuuint32_t boxu[2] = {32, 64};
    encode(fn, &m.u, uaddr, 2, dims, stu, boxu, CU_TENSOR_MAP_SWIZZLE_NONE);
  }
  {
    const cuuint64_t dims[2] = {640, 2048}, st[1] = {1280};
    const cuuint32_t bqm[2] = {64, 128}, bqt[2] = {16, 128}, bom[2] = {64, 16}, bot[2] = {16, 16};
    encode(fn, &m.qm, p.q, 2, dims, st, bqm, CU_TENSOR_MAP_SWIZZLE_128B);
    encode(fn, &m.qt, p.q, 2, dims, st, bqt, CU_TENSOR_MAP_SWIZZLE_32B);
    encode(fn, &m.om, p.out, 2, dims, st, bom, CU_TENSOR_MAP_SWIZZLE_128B);
    encode(fn, &m.ot, p.out, 2, dims, st, bot, CU_TENSOR_MAP_SWIZZLE_32B);
  }
  fused_kernel<<<NCTA, NTHR, SMEM_BYTES>>>(m, p);
}
```

```cpp
#include <cuda.h>
#include <cuda_bf16.h>
#include <cuda_runtime.h>
#include <stdint.h>

namespace {

constexpr int SEQ = 2048, DIM = 640, NCTA = 128, NTHR = 512;

#define TRIG_KB 9
#define KV_KB 2
#define DEV_EXIT 0
#define ATT_GATE 1
#define FENCE_LO 0
#define FENCE_HI 0
#define PW1 2
#define PW2 1
#define ENDBAR 0
#define PAD_KB 0
#define Y_ALIAS 1
#define H_EARLY 1
#define NOMB 0
#define SRC_ROT 0
#define WAIT_NS 0
#define WB_TRIG B_USIG
#define TAILF 1
#define T_ISSUE 384
#define T_PF 416
#define T_INIT 448
#define ATT_MERGE 0
#define BMAP 1
#define PRE2 1
#define KV_MIX 0
#define O_DEFER 0
#define TASK0 0x52
#define TASK1 0x3
#define TASK2 0x41
#define HALO_FIRST 1
#define PREV_EARLY 0
#define ACQ 0
#define U_TMA 0
#define U_GATE 0
#define RF_GATE 0
#define WO_TRIG B_WST
#define WL_TRIG B_WOP
#define WO_GATE 1

constexpr uint32_t STAGE_BYTES = 47104, ST_W = 16384, ST_WT = 40960;
constexpr uint32_t O_BYTES = 20480, WO_BYTES = 12800;
constexpr uint32_t OFF_OA = 0;
constexpr uint32_t OFF_QS = 3 * O_BYTES, OFF_QT = OFF_QS + 16384;
constexpr uint32_t OFF_WC = 81920;
constexpr uint32_t OFF_WA = 94720;
constexpr uint32_t OFF_GATE = 145920;
constexpr uint32_t OFF_TT = 146432;
constexpr uint32_t OFF_KVX = 148480;
constexpr uint32_t OFF_CH3 = 163840;
constexpr uint32_t CH_BYTES = 12288, U_BYTES = 4096;
constexpr uint32_t OFF_FT = 225280, OFF_GT = 229376;
constexpr uint32_t OFF_CH0 = 188416;
constexpr uint32_t OFF_KVS = OFF_CH0, KVS_V = 4480, KVS_BYTES = 8576;
constexpr uint32_t OFF_WS = OFF_WA;
__device__ __forceinline__ uint32_t off_us(int s) { return OFF_CH0 + 4096 * ((0x65320 >> (4 * s)) & 7); }
constexpr uint32_t OFF_YT = 163840;
constexpr uint32_t OFF_BAR = 231936;
constexpr uint32_t SMEM_BYTES = OFF_BAR + 512;

enum : uint32_t {
  B_FULL1 = 0, B_EMPTY1 = 4, B_S3 = 7, B_FULL2 = 52, B_EMPTY2 = 13, B_U = 8, B_GATE = 12, B_HA = 19, B_HB = 20,
  B_ATTN = 21, B_C34 = 22, B_CONV = 23, B_YFULL = 24, B_EPOCH = 25, B_PREP = 26, B_P1 = 27, B_LAST = 28,
  B_E3 = 29, B_OSIG = 30, B_WOP = 31, B_USIG = 32, B_WST = 33, B_KV = 34, B_KVD = 39, B_QF = 17, B_YST = 40,
  B_US = 45, B_YSIG = 50
};
constexpr uint32_t OFF_EPOCH = OFF_BAR + 8 * 51, OFF_D = OFF_BAR + 8 * 60;
__device__ __forceinline__ uint32_t off_o(int j) { return j < 4 ? OFF_OA + j * O_BYTES : j < 6 ? OFF_CH0 + (j - 4) * O_BYTES : OFF_OA + (j - 6) * O_BYTES; }
__device__ __forceinline__ uint32_t off_w(int j) { return j < 4 ? OFF_WA + j * WO_BYTES : j == 4 ? OFF_KVX : j == 5 ? OFF_WC : OFF_WA + (j - 6) * WO_BYTES; }
__device__ __forceinline__ int step_src(int hg, int j) { return SRC_ROT ? (hg + j) & 7 : j == 0 ? hg : j <= hg ? j - 1 : j; }
__device__ __forceinline__ bool tail_first(int hg) { return TAILF && (hg & 3) == 3; }
__device__ __forceinline__ uint32_t off_ch(int c) { return (c < 3 ? OFF_CH0 : OFF_CH3 - 3 * CH_BYTES) + c * CH_BYTES; }

#define U_PITCH 264
__device__ __align__(1024) uint4 g_U[DIM * U_PITCH];
__device__ uint4 g_O[NCTA * 1280];
#define g_Y g_U
constexpr int Y_PITCH = U_PITCH;
__device__ uint4 g_WO[64 * 800];
__device__ uint4 g_halo[NCTA * 2 * 7 * 32];
__device__ float g_gate[SEQ + PAD_KB * 256];
__device__ unsigned g_cnt[32 * (1 + 2 * 16 + 8 + NCTA)];
constexpr int C_LAUNCH = 0, C_PREP = 32, C_Y = 32 * 17, C_W = 32 * 33, C_O = 32 * 41;

#define TSM(cond, slot) do { } while (0)
#define TSIF(cond, slot) do { if (__LINE__ >= FENCE_LO && __LINE__ < FENCE_HI) sched_fence(); } while (0)
__device__ __forceinline__ void sched_fence() {
  asm volatile("{\n.reg .pred p;\n.reg .u32 c;\nmov.u32 c, %%clock;\nsetp.eq.u32 p, c, 0;\n@p st.shared.u32 [%0], c;\n}"
               ::"r"(1024 + OFF_EPOCH + 4) : "memory");
}
#define TS(slot) TSIF(true, slot)

struct Params {
  const __nv_bfloat16 *q, *k, *v, *shift_k, *ssm_k, *ssm_D, *wqkv, *wo, *gate_w;
  __nv_bfloat16* out;
  uint32_t zero;
};

#define POLL_NS 0
constexpr int SPIN_LIMIT = 1 << 17;

__device__ __forceinline__ void mbar_init(uint32_t bar, uint32_t count) {
  asm volatile("mbarrier.init.shared::cta.b64 [%0], %1;" ::"r"(bar), "r"(count) : "memory");
}
__device__ __forceinline__ void mbar_expect_tx(uint32_t bar, uint32_t bytes) {
  asm volatile("mbarrier.arrive.expect_tx.shared::cta.b64 _, [%0], %1;" ::"r"(bar), "r"(bytes) : "memory");
}
__device__ __forceinline__ void mbar_arrive(uint32_t bar) {
  asm volatile("mbarrier.arrive.shared::cta.b64 _, [%0];" ::"r"(bar) : "memory");
}
__device__ __forceinline__ void mbar_wait(uint32_t bar, uint32_t parity) {
  uint32_t ok;
  int spins = 0;
  do {
    if (WAIT_NS)
      asm volatile("{\n.reg .pred p;\nmbarrier.try_wait.parity.shared::cta.b64 p, [%1], %2, %3;\nselp.b32 %0, 1, 0, p;\n}"
                   : "=r"(ok) : "r"(bar), "r"(parity), "r"(WAIT_NS) : "memory");
    else
      asm volatile("{\n.reg .pred p;\nmbarrier.try_wait.parity.shared::cta.b64 p, [%1], %2;\nselp.b32 %0, 1, 0, p;\n}"
                   : "=r"(ok) : "r"(bar), "r"(parity) : "memory");
    if (++spins > SPIN_LIMIT) break;
  } while (!ok);
}
__device__ __forceinline__ unsigned flag_read(const unsigned* p) {
  unsigned v;
  asm volatile("ld.relaxed.gpu.global.u32 %0, [%1];" : "=r"(v) : "l"(p) : "memory");
  return v;
}
__device__ __forceinline__ void flag_poll(const unsigned* p, unsigned target) {
  unsigned v;
  int spins = 0;
  do {
    if (POLL_NS && spins) __nanosleep(POLL_NS);
    asm volatile("ld.relaxed.gpu.global.u32 %0, [%1];" : "=r"(v) : "l"(p) : "memory");
    if (++spins > SPIN_LIMIT) break;
  } while ((int)(v - target) < 0);
}
__device__ __forceinline__ void flag_wait(const unsigned* p, unsigned target) {
  flag_poll(p, target);
  if (ACQ) asm volatile("fence.acquire.gpu;\nfence.proxy.async.global;" ::: "memory");
}
__device__ __forceinline__ void flag_signal(unsigned* p, int n, int lane) {
  if (lane == 0) asm volatile("fence.release.gpu;" ::: "memory");
  __syncwarp();
  if (lane < n) asm volatile("red.relaxed.gpu.global.add.u32 [%0], 1;" ::"l"(p + 32 * lane) : "memory");
}
__device__ __forceinline__ void flag_bump(unsigned* p) {
  asm volatile("red.relaxed.gpu.global.add.u32 [%0], 1;" ::"l"(p) : "memory");
}
__device__ __forceinline__ void fence_async_smem() { asm volatile("fence.proxy.async.shared::cta;" ::: "memory"); }
__device__ __forceinline__ void wg_sync(int id) { asm volatile("bar.sync %0, 128;" ::"r"(id) : "memory"); }

__device__ __forceinline__ void tma_2d(uint32_t dst, const CUtensorMap* tm, int c0, int c1, uint32_t bar) {
  asm volatile("cp.async.bulk.tensor.2d.shared::cluster.global.mbarrier::complete_tx::bytes [%0], [%1, {%3, %4}], [%2];"
               ::"r"(dst), "l"(tm), "r"(bar), "r"(c0), "r"(c1) : "memory");
}
__device__ __forceinline__ void tma_3d(uint32_t dst, const CUtensorMap* tm, int c0, int c1, int c2, uint32_t bar) {
  asm volatile("cp.async.bulk.tensor.3d.shared::cluster.global.mbarrier::complete_tx::bytes [%0], [%1, {%3, %4, %5}], [%2];"
               ::"r"(dst), "l"(tm), "r"(bar), "r"(c0), "r"(c1), "r"(c2) : "memory");
}
__device__ __forceinline__ void bulk_load(uint32_t dst, const void* src, uint32_t bytes, uint32_t bar) {
  asm volatile("cp.async.bulk.shared::cluster.global.mbarrier::complete_tx::bytes [%0], [%1], %2, [%3];"
               ::"r"(dst), "l"(src), "r"(bytes), "r"(bar) : "memory");
}
__device__ __forceinline__ void tm_prefetch(const CUtensorMap* tm) {
  asm volatile("prefetch.tensormap [%0];" ::"l"(tm) : "memory");
}

__device__ __forceinline__ void wg_fence() { asm volatile("wgmma.fence.sync.aligned;" ::: "memory"); }
__device__ __forceinline__ void wg_commit() { asm volatile("wgmma.commit_group.sync.aligned;" ::: "memory"); }
template <int N> __device__ __forceinline__ void wg_wait() { asm volatile("wgmma.wait_group.sync.aligned %0;" ::"n"(N) : "memory"); }
__device__ __forceinline__ uint32_t desc_lo(uint32_t addr, uint32_t lbo) { return ((addr & 0x3FFFF) >> 4) | ((lbo >> 4) << 16); }
constexpr uint32_t desc_hi(uint32_t sbo, uint32_t swz) { return (sbo >> 4) | (swz << 30); }
constexpr uint32_t HI_SW128 = desc_hi(1024, 1), HI_SW64 = desc_hi(512, 2), HI_SW32 = desc_hi(256, 3), HI_NONE = desc_hi(128, 0);
template <int N> __device__ __forceinline__ void pin(float* d) {
#pragma unroll
  for (int i = 0; i < N; i++) asm volatile("" : "+f"(d[i])::"memory");
}

__device__ __forceinline__ uint32_t lds32(uint32_t a) {
  uint32_t v;
  asm volatile("ld.volatile.shared.u32 %0, [%1];" : "=r"(v) : "r"(a) : "memory");
  return v;
}
__device__ __forceinline__ uint4 ldg128(const void* a) {
  uint4 v;
  asm volatile("ld.global.nc.v4.u32 {%0, %1, %2, %3}, [%4];" : "=r"(v.x), "=r"(v.y), "=r"(v.z), "=r"(v.w) : "l"(a) : "memory");
  return v;
}
__device__ __forceinline__ uint2 ldg64(const void* a) {
  uint2 v;
  asm volatile("ld.global.nc.v2.u32 {%0, %1}, [%2];" : "=r"(v.x), "=r"(v.y) : "l"(a) : "memory");
  return v;
}
__device__ __forceinline__ void ldsm4(uint32_t* r, uint32_t a) {
  asm volatile("ldmatrix.sync.aligned.m8n8.x4.shared.b16 {%0, %1, %2, %3}, [%4];"
               : "=r"(r[0]), "=r"(r[1]), "=r"(r[2]), "=r"(r[3]) : "r"(a) : "memory");
}
__device__ __forceinline__ void ldsm4t(uint32_t* r, uint32_t a) {
  asm volatile("ldmatrix.sync.aligned.m8n8.x4.trans.shared.b16 {%0, %1, %2, %3}, [%4];"
               : "=r"(r[0]), "=r"(r[1]), "=r"(r[2]), "=r"(r[3]) : "r"(a) : "memory");
}
__device__ __forceinline__ uint4 lds128(uint32_t a) {
  uint4 v;
  asm volatile("ld.shared.v4.u32 {%0, %1, %2, %3}, [%4];" : "=r"(v.x), "=r"(v.y), "=r"(v.z), "=r"(v.w) : "r"(a) : "memory");
  return v;
}
__device__ __forceinline__ void sts128(uint32_t a, uint32_t x, uint32_t y, uint32_t z, uint32_t w) {
  asm volatile("st.shared.v4.u32 [%0], {%1, %2, %3, %4};" ::"r"(a), "r"(x), "r"(y), "r"(z), "r"(w) : "memory");
}
__device__ __forceinline__ void stsm4(uint32_t a, const uint32_t* r) {
  asm volatile("stmatrix.sync.aligned.m8n8.x4.shared.b16 [%0], {%1, %2, %3, %4};" ::"r"(a), "r"(r[0]), "r"(r[1]), "r"(r[2]), "r"(r[3]) : "memory");
}
__device__ __forceinline__ void stsm4t(uint32_t a, const uint32_t* r) {
  asm volatile("stmatrix.sync.aligned.m8n8.x4.trans.shared.b16 [%0], {%1, %2, %3, %4};" ::"r"(a), "r"(r[0]), "r"(r[1]), "r"(r[2]), "r"(r[3]) : "memory");
}
__device__ __forceinline__ uint32_t pack2(float lo, float hi) {
  uint32_t r;
  asm("cvt.rn.bf16x2.f32 %0, %1, %2;" : "=r"(r) : "f"(hi), "f"(lo));
  return r;
}
__device__ __forceinline__ uint32_t movm(uint32_t a) {
  uint32_t d;
  asm volatile("movmatrix.sync.aligned.m8n8.trans.b16 %0, %1;" : "=r"(d) : "r"(a));
  return d;
}
__device__ __forceinline__ uint32_t bmul(uint32_t a, uint32_t b) {
  uint32_t d;
  asm("mul.rn.bf16x2 %0, %1, %2;" : "=r"(d) : "r"(a), "r"(b));
  return d;
}
__device__ __forceinline__ uint32_t badd(uint32_t a, uint32_t b) {
  uint32_t d;
  asm("add.rn.bf16x2 %0, %1, %2;" : "=r"(d) : "r"(a), "r"(b));
  return d;
}
__device__ __forceinline__ float bf_lo(uint32_t x) { return __uint_as_float(x << 16); }
__device__ __forceinline__ float bf_hi(uint32_t x) { return __uint_as_float(x & 0xFFFF0000u); }
__device__ __forceinline__ float ex2(float x) {
  float y;
  asm("ex2.approx.ftz.f32 %0, %1;" : "=f"(y) : "f"(x));
  return y;
}
__device__ __forceinline__ float rcp(float x) {
  float y;
  asm("rcp.approx.ftz.f32 %0, %1;" : "=f"(y) : "f"(x));
  return y;
}
__device__ __forceinline__ void mma16816(float* d, uint32_t a0, uint32_t a1, uint32_t a2, uint32_t a3, uint32_t b0, uint32_t b1) {
  asm volatile("mma.sync.aligned.m16n8k16.row.col.f32.bf16.bf16.f32 {%0, %1, %2, %3}, {%4, %5, %6, %7}, {%8, %9}, {%0, %1, %2, %3};"
               : "+f"(d[0]), "+f"(d[1]), "+f"(d[2]), "+f"(d[3])
               : "r"(a0), "r"(a1), "r"(a2), "r"(a3), "r"(b0), "r"(b1));
}
__device__ __forceinline__ void mma1688(float* d, uint32_t a0, uint32_t a1, uint32_t b0) {
  asm volatile("mma.sync.aligned.m16n8k8.row.col.f32.bf16.bf16.f32 {%0, %1, %2, %3}, {%4, %5}, {%6}, {%0, %1, %2, %3};"
               : "+f"(d[0]), "+f"(d[1]), "+f"(d[2]), "+f"(d[3])
               : "r"(a0), "r"(a1), "r"(b0));
}

template <int N> struct WgRS;
template <int N> struct WgSST;
template <> struct WgRS<32> {
  template <uint32_t HB>
  static __device__ __forceinline__ void mma(float* d, const uint32_t* a, uint32_t db) {
    asm volatile("{\n.reg .pred p;\n.reg .b64 db;\nsetp.ne.b32 p, %22, 0;\n"
      "mov.b64 db, {%20, %21};\n"
      "wgmma.mma_async.sync.aligned.m64n32k16.f32.bf16.bf16 {"
      "%0, %1, %2, %3, %4, %5, %6, %7, %8, %9, %10, %11, %12, %13, %14, %15"
      "}, {%16, %17, %18, %19}, db, p, 1, 1, 1;\n}\n"
      : "+f"(d[0]), "+f"(d[1]), "+f"(d[2]), "+f"(d[3]), "+f"(d[4]), "+f"(d[5]), "+f"(d[6]), "+f"(d[7]),
        "+f"(d[8]), "+f"(d[9]), "+f"(d[10]), "+f"(d[11]), "+f"(d[12]), "+f"(d[13]), "+f"(d[14]), "+f"(d[15])
      : "r"(a[0]), "r"(a[1]), "r"(a[2]), "r"(a[3]), "r"(db), "n"(HB), "n"(1));
  }
  template <uint32_t HB>
  static __device__ __forceinline__ void set(float* d, const uint32_t* a, uint32_t db) {
    asm volatile("{\n.reg .pred p;\n.reg .b64 db;\nsetp.ne.b32 p, %22, 0;\n"
      "mov.b64 db, {%20, %21};\n"
      "wgmma.mma_async.sync.aligned.m64n32k16.f32.bf16.bf16 {"
      "%0, %1, %2, %3, %4, %5, %6, %7, %8, %9, %10, %11, %12, %13, %14, %15"
      "}, {%16, %17, %18, %19}, db, p, 1, 1, 1;\n}\n"
      : "=f"(d[0]), "=f"(d[1]), "=f"(d[2]), "=f"(d[3]), "=f"(d[4]), "=f"(d[5]), "=f"(d[6]), "=f"(d[7]),
        "=f"(d[8]), "=f"(d[9]), "=f"(d[10]), "=f"(d[11]), "=f"(d[12]), "=f"(d[13]), "=f"(d[14]), "=f"(d[15])
      : "r"(a[0]), "r"(a[1]), "r"(a[2]), "r"(a[3]), "r"(db), "n"(HB), "n"(0));
  }
};
template <> struct WgRS<64> {
  template <uint32_t HB>
  static __device__ __forceinline__ void mma(float* d, const uint32_t* a, uint32_t db) {
    asm volatile("{\n.reg .pred p;\n.reg .b64 db;\nsetp.ne.b32 p, %38, 0;\n"
      "mov.b64 db, {%36, %37};\n"
      "wgmma.mma_async.sync.aligned.m64n64k16.f32.bf16.bf16 {"
      "%0, %1, %2, %3, %4, %5, %6, %7, %8, %9, %10, %11, %12, %13, %14, %15, "
      "%16, %17, %18, %19, %20, %21, %22, %23, %24, %25, %26, %27, %28, %29, %30, %31"
      "}, {%32, %33, %34, %35}, db, p, 1, 1, 1;\n}\n"
      : "+f"(d[0]), "+f"(d[1]), "+f"(d[2]), "+f"(d[3]), "+f"(d[4]), "+f"(d[5]), "+f"(d[6]), "+f"(d[7]),
        "+f"(d[8]), "+f"(d[9]), "+f"(d[10]), "+f"(d[11]), "+f"(d[12]), "+f"(d[13]), "+f"(d[14]), "+f"(d[15]),
        "+f"(d[16]), "+f"(d[17]), "+f"(d[18]), "+f"(d[19]), "+f"(d[20]), "+f"(d[21]), "+f"(d[22]), "+f"(d[23]),
        "+f"(d[24]), "+f"(d[25]), "+f"(d[26]), "+f"(d[27]), "+f"(d[28]), "+f"(d[29]), "+f"(d[30]), "+f"(d[31])
      : "r"(a[0]), "r"(a[1]), "r"(a[2]), "r"(a[3]), "r"(db), "n"(HB), "n"(1));
  }
  template <uint32_t HB>
  static __device__ __forceinline__ void set(float* d, const uint32_t* a, uint32_t db) {
    asm volatile("{\n.reg .pred p;\n.reg .b64 db;\nsetp.ne.b32 p, %38, 0;\n"
      "mov.b64 db, {%36, %37};\n"
      "wgmma.mma_async.sync.aligned.m64n64k16.f32.bf16.bf16 {"
      "%0, %1, %2, %3, %4, %5, %6, %7, %8, %9, %10, %11, %12, %13, %14, %15, "
      "%16, %17, %18, %19, %20, %21, %22, %23, %24, %25, %26, %27, %28, %29, %30, %31"
      "}, {%32, %33, %34, %35}, db, p, 1, 1, 1;\n}\n"
      : "=f"(d[0]), "=f"(d[1]), "=f"(d[2]), "=f"(d[3]), "=f"(d[4]), "=f"(d[5]), "=f"(d[6]), "=f"(d[7]),
        "=f"(d[8]), "=f"(d[9]), "=f"(d[10]), "=f"(d[11]), "=f"(d[12]), "=f"(d[13]), "=f"(d[14]), "=f"(d[15]),
        "=f"(d[16]), "=f"(d[17]), "=f"(d[18]), "=f"(d[19]), "=f"(d[20]), "=f"(d[21]), "=f"(d[22]), "=f"(d[23]),
        "=f"(d[24]), "=f"(d[25]), "=f"(d[26]), "=f"(d[27]), "=f"(d[28]), "=f"(d[29]), "=f"(d[30]), "=f"(d[31])
      : "r"(a[0]), "r"(a[1]), "r"(a[2]), "r"(a[3]), "r"(db), "n"(HB), "n"(0));
  }
};
template <> struct WgSST<48> {
  template <uint32_t HA, uint32_t HB>
  static __device__ __forceinline__ void mma(float* d, uint32_t da, uint32_t db, int sc) {
    asm volatile("{\n.reg .pred p;\n.reg .b64 da, db;\nsetp.ne.b32 p, %28, 0;\n"
      "mov.b64 da, {%24, %25};\nmov.b64 db, {%26, %27};\n"
      "wgmma.mma_async.sync.aligned.m64n48k16.f32.bf16.bf16 {"
      "%0, %1, %2, %3, %4, %5, %6, %7, %8, %9, %10, %11, %12, %13, %14, %15, "
      "%16, %17, %18, %19, %20, %21, %22, %23"
      "}, da, db, p, 1, 1, 0, 1;\n}\n"
      : "+f"(d[0]), "+f"(d[1]), "+f"(d[2]), "+f"(d[3]), "+f"(d[4]), "+f"(d[5]), "+f"(d[6]), "+f"(d[7]),
        "+f"(d[8]), "+f"(d[9]), "+f"(d[10]), "+f"(d[11]), "+f"(d[12]), "+f"(d[13]), "+f"(d[14]), "+f"(d[15]),
        "+f"(d[16]), "+f"(d[17]), "+f"(d[18]), "+f"(d[19]), "+f"(d[20]), "+f"(d[21]), "+f"(d[22]), "+f"(d[23])
      : "r"(da), "n"(HA), "r"(db), "n"(HB), "r"(sc));
  }
};
template <> struct WgSST<80> {
  template <uint32_t HA, uint32_t HB>
  static __device__ __forceinline__ void mma(float* d, uint32_t da, uint32_t db, int sc) {
    asm volatile("{\n.reg .pred p;\n.reg .b64 da, db;\nsetp.ne.b32 p, %44, 0;\n"
      "mov.b64 da, {%40, %41};\nmov.b64 db, {%42, %43};\n"
      "wgmma.mma_async.sync.aligned.m64n80k16.f32.bf16.bf16 {"
      "%0, %1, %2, %3, %4, %5, %6, %7, %8, %9, %10, %11, %12, %13, %14, %15, "
      "%16, %17, %18, %19, %20, %21, %22, %23, %24, %25, %26, %27, %28, %29, %30, %31, "
      "%32, %33, %34, %35, %36, %37, %38, %39"
      "}, da, db, p, 1, 1, 0, 1;\n}\n"
      : "+f"(d[0]), "+f"(d[1]), "+f"(d[2]), "+f"(d[3]), "+f"(d[4]), "+f"(d[5]), "+f"(d[6]), "+f"(d[7]),
        "+f"(d[8]), "+f"(d[9]), "+f"(d[10]), "+f"(d[11]), "+f"(d[12]), "+f"(d[13]), "+f"(d[14]), "+f"(d[15]),
        "+f"(d[16]), "+f"(d[17]), "+f"(d[18]), "+f"(d[19]), "+f"(d[20]), "+f"(d[21]), "+f"(d[22]), "+f"(d[23]),
        "+f"(d[24]), "+f"(d[25]), "+f"(d[26]), "+f"(d[27]), "+f"(d[28]), "+f"(d[29]), "+f"(d[30]), "+f"(d[31]),
        "+f"(d[32]), "+f"(d[33]), "+f"(d[34]), "+f"(d[35]), "+f"(d[36]), "+f"(d[37]), "+f"(d[38]), "+f"(d[39])
      : "r"(da), "n"(HA), "r"(db), "n"(HB), "r"(sc));
  }
};
template <> struct WgSST<192> {
  template <uint32_t HA, uint32_t HB>
  static __device__ __forceinline__ void mma(float* d, uint32_t da, uint32_t db, int sc) {
    asm volatile("{\n.reg .pred p;\n.reg .b64 da, db;\nsetp.ne.b32 p, %100, 0;\n"
      "mov.b64 da, {%96, %97};\nmov.b64 db, {%98, %99};\n"
      "wgmma.mma_async.sync.aligned.m64n192k16.f32.bf16.bf16 {"
      "%0, %1, %2, %3, %4, %5, %6, %7, %8, %9, %10, %11, %12, %13, %14, %15, "
      "%16, %17, %18, %19, %20, %21, %22, %23, %24, %25, %26, %27, %28, %29, %30, %31, "
      "%32, %33, %34, %35, %36, %37, %38, %39, %40, %41, %42, %43, %44, %45, %46, %47, "
      "%48, %49, %50, %51, %52, %53, %54, %55, %56, %57, %58, %59, %60, %61, %62, %63, "
      "%64, %65, %66, %67, %68, %69, %70, %71, %72, %73, %74, %75, %76, %77, %78, %79, "
      "%80, %81, %82, %83, %84, %85, %86, %87, %88, %89, %90, %91, %92, %93, %94, %95"
      "}, da, db, p, 1, 1, 0, 1;\n}\n"
      : "+f"(d[0]), "+f"(d[1]), "+f"(d[2]), "+f"(d[3]), "+f"(d[4]), "+f"(d[5]), "+f"(d[6]), "+f"(d[7]),
        "+f"(d[8]), "+f"(d[9]), "+f"(d[10]), "+f"(d[11]), "+f"(d[12]), "+f"(d[13]), "+f"(d[14]), "+f"(d[15]),
        "+f"(d[16]), "+f"(d[17]), "+f"(d[18]), "+f"(d[19]), "+f"(d[20]), "+f"(d[21]), "+f"(d[22]), "+f"(d[23]),
        "+f"(d[24]), "+f"(d[25]), "+f"(d[26]), "+f"(d[27]), "+f"(d[28]), "+f"(d[29]), "+f"(d[30]), "+f"(d[31]),
        "+f"(d[32]), "+f"(d[33]), "+f"(d[34]), "+f"(d[35]), "+f"(d[36]), "+f"(d[37]), "+f"(d[38]), "+f"(d[39]),
        "+f"(d[40]), "+f"(d[41]), "+f"(d[42]), "+f"(d[43]), "+f"(d[44]), "+f"(d[45]), "+f"(d[46]), "+f"(d[47]),
        "+f"(d[48]), "+f"(d[49]), "+f"(d[50]), "+f"(d[51]), "+f"(d[52]), "+f"(d[53]), "+f"(d[54]), "+f"(d[55]),
        "+f"(d[56]), "+f"(d[57]), "+f"(d[58]), "+f"(d[59]), "+f"(d[60]), "+f"(d[61]), "+f"(d[62]), "+f"(d[63]),
        "+f"(d[64]), "+f"(d[65]), "+f"(d[66]), "+f"(d[67]), "+f"(d[68]), "+f"(d[69]), "+f"(d[70]), "+f"(d[71]),
        "+f"(d[72]), "+f"(d[73]), "+f"(d[74]), "+f"(d[75]), "+f"(d[76]), "+f"(d[77]), "+f"(d[78]), "+f"(d[79]),
        "+f"(d[80]), "+f"(d[81]), "+f"(d[82]), "+f"(d[83]), "+f"(d[84]), "+f"(d[85]), "+f"(d[86]), "+f"(d[87]),
        "+f"(d[88]), "+f"(d[89]), "+f"(d[90]), "+f"(d[91]), "+f"(d[92]), "+f"(d[93]), "+f"(d[94]), "+f"(d[95])
      : "r"(da), "n"(HA), "r"(db), "n"(HB), "r"(sc));
  }
};

struct FftConst {
  uint32_t f[2][4], fi[4][4];
  float ta[4], tb[4];
};
__device__ __forceinline__ void cis(int m, float scale, float& c, float& s) {
  const float a = (float)m * (-6.283185307179586f * scale);
  c = __cosf(a);
  s = __sinf(a);
}
__device__ __forceinline__ void fft_tables(uint32_t (&v)[12], int tw) {
  const int row = tw >> 2, ch = tw & 3;
#pragma unroll
  for (int i = 0; i < 4; i++) {
    float c[2], s[2], x[2];
#pragma unroll
    for (int e = 0; e < 2; e++) {
      cis((((32 * (8 * ch + 2 * i + e) + 15) * (4 * row - 63) + 2048) & 4095) - 2048, 1.f / 4096, c[e], s[e]);
      float gc, gs;
      cis((((row & 15) * (8 * (ch & 1) + 2 * i + e) + 8) & 15) - 8, 1.f / 16, gc, gs);
      x[e] = (row >> 4) == (ch >> 1) ? gc : (ch >> 1) ? gs : -gs;
    }
    v[i] = pack2(c[0] * 0.125f, c[1] * 0.125f);
    v[4 + i] = pack2(s[0] * 0.125f, s[1] * 0.125f);
    v[8 + i] = pack2(x[0], x[1]);
  }
#pragma unroll
  for (int i = 0; i < 12; i++) asm volatile("" : "+r"(v[i]));
}
__device__ __forceinline__ void fft_tables_store(const uint32_t (&v)[12], uint32_t sb, int tw) {
  const int row = tw >> 2;
  const uint32_t x = ((tw ^ (row >> 1)) & 3) << 4, a = sb + OFF_FT + (16 * (row >> 3) + (row & 7)) * 64 + x;
  sts128(a, v[0], v[1], v[2], v[3]);
  sts128(a + 512, v[4], v[5], v[6], v[7]);
  sts128(sb + OFF_GT + row * 64 + x, v[8], v[9], v[10], v[11]);
}
__device__ __forceinline__ void fft_twiddles(float (&v)[4], int tw) {
#pragma unroll
  for (int i = 0; i < 2; i++) {
    float c, s;
    cis((2 * (2 * (tw & 3) + i) - 15) * (4 * (tw >> 2) - 63), 1.f / 4096, c, s);
    v[2 * i] = __fdividef(-s, 1.f + c);
    v[2 * i + 1] = s;
  }
  pin<4>(v);
}
__device__ __forceinline__ void fft_matrices(FftConst& k, uint32_t sb, int w, int lane) {
  const uint32_t x = (lane >> 1) & 3;
  const uint4 t0 = lds128(sb + OFF_TT + 512 * w + 16 * lane), t1 = lds128(sb + OFF_TT + 512 * w + 16 * (lane ^ 3));
  k.ta[0] = __uint_as_float(t0.x); k.tb[0] = __uint_as_float(t0.y); k.ta[1] = __uint_as_float(t0.z); k.tb[1] = __uint_as_float(t0.w);
  k.ta[3] = __uint_as_float(t1.x); k.tb[3] = __uint_as_float(t1.y); k.ta[2] = __uint_as_float(t1.z); k.tb[2] = __uint_as_float(t1.w);
#pragma unroll
  for (int i = 0; i < 2; i++) {
    ldsm4(k.f[i], sb + OFF_FT + (16 * w + (lane & 15)) * 64 + (((2 * i + (lane >> 4)) ^ x) << 4));
    ldsm4t(k.fi[i], sb + OFF_FT + (32 * i + lane) * 64 + ((w ^ x) << 4));
#pragma unroll
    for (int j = 0; j < 4; j++) {
      k.fi[2 + i][j] = (j & 1) ? k.fi[i][j - 1] ^ 0x80008000u : k.fi[i][j + 1];
      asm volatile("" : "+r"(k.fi[2 + i][j]));
    }
  }
}
__device__ __forceinline__ void rot(bool inv, float& x, float& y, float a, float b) {
  x = fmaf(inv ? -a : a, y, x);
  y = fmaf(inv ? -b : b, x, y);
  x = fmaf(inv ? -a : a, y, x);
}
__device__ __forceinline__ void twiddle_fwd(uint32_t (&a)[4][4], float* d, const FftConst& k) {
#pragma unroll
  for (int q = 0; q < 4; q++)
#pragma unroll
    for (int j = 0; j < 2; j++) {
      float* x = d + 8 * q + 4 * j;
      rot(j, x[0], x[2], k.ta[2 * j], k.tb[2 * j]);
      rot(j, x[1], x[3], k.ta[2 * j + 1], k.tb[2 * j + 1]);
      a[q & 2][2 * j + (q & 1)] = pack2(x[0], x[1]);
      a[(q & 2) + 1][2 * j + (q & 1)] = pack2(x[2], x[3]);
    }
}
__device__ __forceinline__ void g_step(float* d, const uint32_t (&a)[4][4], uint32_t dre, uint32_t dim) {
  WgRS<32>::set<HI_SW64>(d, a[0], dre);
  WgRS<32>::set<HI_SW64>(d + 16, a[2], dre);
  WgRS<32>::mma<HI_SW64>(d, a[1], dim);
  WgRS<32>::mma<HI_SW64>(d + 16, a[3], dim);
  wg_commit();
}

__device__ __forceinline__ void conv_channel(const FftConst& k, uint32_t sb, int c, int wg, int w, int lane) {
  const uint32_t cb = sb + off_ch(c), bars = sb + OFF_BAR;
  const uint32_t du = desc_lo(cb, 1024), dg = desc_lo(sb + OFF_GT, 16), dz = desc_lo(cb + U_BYTES, 16);
  float U[32], H[32];
  uint32_t a[4][4], e[4][4];
  const float dv = __uint_as_float(lds32(sb + OFF_D + 4 * c));
  wg_fence();
  WgRS<64>::set<HI_SW32>(H, k.f[0], du + 256);
  WgRS<64>::mma<HI_SW32>(H, k.f[1], du + 256 + 32);
  wg_commit();
  wg_wait<0>();
  pin<32>(H);
  twiddle_fwd(a, H, k);
  if (ATT_GATE && H_EARLY) mbar_wait(bars + 8 * B_ATTN, 0);
  mbar_wait(bars + 8 * (B_U + (c < 3 ? c : 3)), 0);
  TSM(w == 0 && c < 3, 7 + wg);
  wg_fence();
  WgRS<64>::set<HI_SW32>(U, k.f[0], du);
  WgRS<64>::mma<HI_SW32>(U, k.f[1], du + 32);
  wg_commit();
  g_step(H, a, dg, dg + 64);
  wg_wait<1>();
  pin<32>(U);
  twiddle_fwd(e, U, k);
  wg_fence();
  g_step(U, e, dg, dg + 64);
  wg_wait<0>();
  pin<32>(U);
  pin<32>(H);
#pragma unroll
  for (int j = 0; j < 2; j++) {
    float pr[4][2], pi[4][2];
#pragma unroll
    for (int x = 0; x < 2; x++) {
      H[4 * j + x] += dv;
#pragma unroll
      for (int m = 0; m < 4; m++) {
#pragma unroll
        for (int q = 0; q <= m; q++) {
          const int ih = 16 * (q >> 1) + 2 * (q & 1) + 4 * j + x, iu = 16 * ((m - q) >> 1) + 2 * ((m - q) & 1) + 4 * j + x;
          pr[m][x] = q ? fmaf(H[ih], U[iu], pr[m][x]) : H[ih] * U[iu];
          pi[m][x] = q ? fmaf(H[ih], U[iu + 8], pi[m][x]) : H[ih] * U[iu + 8];
          pr[m][x] = fmaf(-H[ih + 8], U[iu + 8], pr[m][x]);
          pi[m][x] = fmaf(H[ih + 8], U[iu], pi[m][x]);
        }
      }
    }
#pragma unroll
    for (int m = 0; m < 4; m++) {
      a[m & 2][2 * j + (m & 1)] = pack2(pr[m][0], pr[m][1]);
      a[(m & 2) + 1][2 * j + (m & 1)] = pack2(pi[m][0], pi[m][1]);
    }
  }
  wg_fence();
  g_step(U, a, dg + 64, dg);
  const uint32_t za = cb + U_BYTES + (8 * w + (lane & 7)) * 128 + (((lane >> 3) ^ (lane & 7)) << 4);
  const uint32_t ya = cb + (lane >> 4) * 1024 + (8 * w + (lane & 7)) * 32 + ((((lane >> 3) ^ (lane >> 2)) & 1) << 4);
  wg_sync(1 + wg);
  wg_wait<0>();
  pin<32>(U);
  TSIF(w == 0, 80 + c);
#pragma unroll
  for (int p = 0; p < 2; p++) {
#pragma unroll
    for (int i = 0; i < 4; i++) {
      const int j = i & 1;
      float* x = U + 16 * p + 4 * j + (i & 2);
      rot(!j, x[8], x[0], k.ta[2 * j], k.tb[2 * j]);
      rot(!j, x[9], x[1], k.ta[2 * j + 1], k.tb[2 * j + 1]);
      e[p][i] = pack2(x[8], x[9]);
      e[2 + p][i] = pack2(x[0], x[1]);
    }
    stsm4(za ^ (64 * p), e[p]);
    stsm4((za ^ (64 * p)) + 4096, e[2 + p]);
  }
  fence_async_smem();
  wg_sync(1 + wg);
  wg_fence();
  WgRS<64>::set<HI_SW128>(H, k.fi[0], dz);
#pragma unroll
  for (int ks = 1; ks < 4; ks++) WgRS<64>::mma<HI_SW128>(H, k.fi[ks], dz + 128 * ks);
  wg_commit();
  wg_wait<0>();
  pin<32>(H);
  TSIF(w == 0, 88 + c);
#pragma unroll
  for (int j = 0; j < 8; j++)
    a[j >> 2][j & 3] = j < 2 ? pack2(H[4 * j], H[4 * j + 1]) : pack2(H[4 * j] + H[4 * j - 6], H[4 * j + 1] + H[4 * j - 5]);
  stsm4(ya, a[0]);
  stsm4(ya + 2048, a[1]);
  fence_async_smem();
  __syncwarp();
}

__device__ __forceinline__ void prep_slab(uint4* res, const uint2* sw, uint32_t sb, int slab, int w, int lane) {
  const int t = lane & 3, tp = (lane & 7) >> 1, pos = 8 * tp + 2 * (((lane >> 3) + tp) & 3) + (lane & 1);
  const uint32_t base = sb + OFF_KVS + slab * KVS_BYTES + pos * 128;
  uint32_t kk[2][4][4], vv[2][4];
  mbar_wait(sb + OFF_BAR + 8 * (B_KV + slab), 0);
#pragma unroll
  for (int h = 0; h < 2; h++) {
#pragma unroll
    for (int j = 0; j < 4; j++) {
      const uint32_t a = base + 128 * j;
      ldsm4t(kk[h][j], a + (((w + 4 * h) ^ ((a >> 7) & 7)) << 4));
    }
    const uint32_t a = base + KVS_V;
    ldsm4t(vv[h], a + (((w + 4 * h) ^ ((a >> 7) & 7)) << 4));
  }
#pragma unroll
  for (int h = 0; h < 2; h++) {
    uint32_t (&k)[4][4] = kk[h];
    uint32_t (&v)[4] = vv[h];
    const uint32_t w0 = __byte_perm(sw[h].x, 0, 0x1010), w1 = __byte_perm(sw[h].x, 0, 0x3232);
    const uint32_t w2 = __byte_perm(sw[h].y, 0, 0x1010), w3 = __byte_perm(sw[h].y, 0, 0x3232);
#pragma unroll
    for (int m = 0; m < 4; m++)
      v[m] = bmul(badd(badd(badd(bmul(k[0][m], w3), bmul(k[1][m], w2)), bmul(k[2][m], w1)), bmul(k[3][m], w0)), v[m]);
    uint32_t a[4];
#pragma unroll
    for (int m = 0; m < 4; m++) a[m] = (t & 1) ? v[(m + 3) & 3] : v[m];
    res[h] = (t & 2) ? make_uint4(a[2], a[3], a[0], a[1]) : make_uint4(a[0], a[1], a[2], a[3]);
  }
}

__device__ __forceinline__ void gate_step(float& z, uint4& gw, const Params& p, uint32_t sb, uint32_t xa, int kb, int lane) {
  mbar_wait(sb + OFF_BAR + 8 * (B_FULL1 + (kb & 3)), (kb >> 2) & 1);
  const uint4 x = lds128(xa + (kb & 3) * STAGE_BYTES);
  const uint32_t m0 = bmul(x.x, gw.x), m1 = bmul(x.y, gw.y), m2 = bmul(x.z, gw.z), m3 = bmul(x.w, gw.w);
  if (kb < 9) gw = ldg128(reinterpret_cast<const uint4*>(p.gate_w) + 8 * (kb + 1) + (lane & 7));
  z += ((bf_lo(m0) + bf_hi(m0)) + (bf_lo(m1) + bf_hi(m1))) + ((bf_lo(m2) + bf_hi(m2)) + (bf_lo(m3) + bf_hi(m3)));
  __syncwarp();
  if (lane == 0) mbar_arrive(sb + OFF_BAR + 8 * (kb == 3 ? B_E3 : kb == 9 ? B_P1 : B_EMPTY1 + (kb & 3)) + (x.x & p.zero));
}

__device__ __forceinline__ uint32_t bmax(uint32_t a, uint32_t b) {
  uint32_t d;
  asm("max.bf16x2 %0, %1, %2;" : "=r"(d) : "r"(a), "r"(b));
  return d;
}
__device__ __forceinline__ void softmax_two(const float (&l)[2][2], uint32_t& p0, uint32_t& p1) {
  constexpr float kScale = 0.22360679774997896f, kLog2e = 1.4426950408889634f;
  const uint32_t r0 = pack2(l[0][0], l[1][0]), r1 = pack2(l[0][1], l[1][1]);
  const uint32_t x0 = pack2(bf_lo(r0) * kScale, bf_hi(r0) * kScale), x1 = pack2(bf_lo(r1) * kScale, bf_hi(r1) * kScale);
  uint32_t m = bmax(x0, x1);
  m = bmax(m, __shfl_xor_sync(0xffffffffu, m, 1));
  m = bmax(m, __shfl_xor_sync(0xffffffffu, m, 2));
  const float m0 = bf_lo(m) * kLog2e, m1 = bf_hi(m) * kLog2e;
  p0 = pack2(ex2(bf_lo(x0) * kLog2e - m0), ex2(bf_lo(x1) * kLog2e - m0));
  p1 = pack2(ex2(bf_hi(x0) * kLog2e - m1), ex2(bf_hi(x1) * kLog2e - m1));
}

__device__ __forceinline__ void halo_read(uint32_t (&kpv)[10], uint32_t (&vpv)[10], uint32_t (&tg)[7], const uint4* hp) {
#pragma unroll
  for (int j = 0; j < 7; j++) {
    uint32_t x0, x1, x2;
    asm volatile("ld.relaxed.gpu.global.v4.u32 {%0, %1, %2, %3}, [%4];"
                 : "=r"(x0), "=r"(x1), "=r"(x2), "=r"(tg[j]) : "l"(hp + 32 * j) : "memory");
    if (j < 4) kpv[3 * j] = x0; else vpv[3 * j - 10] = x0;
    if (j < 3) kpv[3 * j + 1] = x1; else vpv[3 * j - 9] = x1;
    if (j < 3) kpv[3 * j + 2] = x2; else if (j < 6) vpv[3 * j - 8] = x2;
  }
}

template <int ROT>
__device__ __forceinline__ void pack_qkv(const float* acc, uint32_t (&qlo)[10], uint32_t (&qhi)[10], uint32_t (&klo)[10],
                                         uint32_t (&khi)[10], uint32_t (&vlo)[10], uint32_t (&vhi)[10]) {
#pragma unroll
  for (int j = 0; j < 10; j++) {
    const int x = (j + ROT) % 10, tq = x < 8 ? x : 16 + x, tk = x < 8 ? 8 + x : 18 + x, tv = x < 8 ? 16 + x : 20 + x;
    khi[j] = pack2(acc[4 * tk + 2], acc[4 * tk + 3]);
    vhi[j] = movm(pack2(acc[4 * tv + 2], acc[4 * tv + 3]));
    qlo[j] = pack2(acc[4 * tq], acc[4 * tq + 1]);
    qhi[j] = pack2(acc[4 * tq + 2], acc[4 * tq + 3]);
    klo[j] = pack2(acc[4 * tk], acc[4 * tk + 1]);
    vlo[j] = pack2(acc[4 * tv], acc[4 * tv + 1]);
    asm volatile("" : "+r"(khi[j]), "+r"(qlo[j]), "+r"(qhi[j]), "+r"(klo[j]), "+r"(vlo[j]));
  }
}

template <int ROT> __device__ __forceinline__ void halo_send(const float* acc, uint4* ho, uint32_t tag) {
#pragma unroll
  for (int j = 0; j < 7; j++) {
    uint32_t x[3];
#pragma unroll
    for (int e = 0; e < 3; e++) {
      const int i = 3 * j + e, y = (i % 10 + ROT) % 10, tk = y < 8 ? 8 + y : 18 + y, tv = y < 8 ? 16 + y : 20 + y;
      x[e] = i < 10 ? pack2(acc[4 * tk + 2], acc[4 * tk + 3]) : i < 20 ? movm(pack2(acc[4 * tv + 2], acc[4 * tv + 3])) : 0u;
    }
    asm volatile("st.relaxed.gpu.global.v4.u32 [%0], {%1, %2, %3, %4};" ::"l"(ho + 32 * j), "r"(x[0]), "r"(x[1]), "r"(x[2]), "r"(tag) : "memory");
  }
}

__device__ __forceinline__ void attention(float* acc, uint32_t sb, int b, int par, int w, int lane, uint32_t tag) {
  const int g = lane >> 2, t = lane & 3;
  uint32_t klo[10], khi[10], vlo[10], vhi[10], qlo[10], qhi[10], kpv[10], vpv[10];
  if (HALO_FIRST && w == 3 && b < NCTA - 8) {
    uint4* ho = g_halo + (b * 2 + par) * 224 + lane;
    if (tail_first(b & 7)) halo_send<8>(acc, ho, tag);
    else halo_send<0>(acc, ho, tag);
    TSIF(par == 0, 76);
    pin<120>(acc);
  }
  if (tail_first(b & 7)) pack_qkv<8>(acc, qlo, qhi, klo, khi, vlo, vhi);
  else pack_qkv<0>(acc, qlo, qhi, klo, khi, vlo, vhi);
  const uint32_t xa = sb + OFF_KVX + (par * 3) * 2560 + lane * 16;
  if (w < 3) {
    sts128(xa + w * 2560, khi[0], khi[1], khi[2], khi[3]);
    sts128(xa + w * 2560 + 512, khi[4], khi[5], khi[6], khi[7]);
    sts128(xa + w * 2560 + 1024, khi[8], khi[9], vhi[0], vhi[1]);
    sts128(xa + w * 2560 + 1536, vhi[2], vhi[3], vhi[4], vhi[5]);
    sts128(xa + w * 2560 + 2048, vhi[6], vhi[7], vhi[8], vhi[9]);
  } else if (!HALO_FIRST && b < NCTA - 8) {
    uint4* ho = g_halo + (b * 2 + par) * 224 + lane;
#pragma unroll
    for (int j = 0; j < 7; j++) {
      const uint32_t x0 = j < 4 ? khi[3 * j] : vhi[3 * j - 10], x1 = j < 3 ? khi[3 * j + 1] : vhi[3 * j - 9];
      const uint32_t x2 = j < 3 ? khi[3 * j + 2] : j < 6 ? vhi[3 * j - 8] : 0u;
      asm volatile("st.relaxed.gpu.global.v4.u32 [%0], {%1, %2, %3, %4};" ::"l"(ho + 32 * j), "r"(x0), "r"(x1), "r"(x2), "r"(tag) : "memory");
    }
  }
  TSIF(par == 0 && w == 1, 64);
  TSIF(par == 0 && w == 3 && !HALO_FIRST, 76);
#pragma unroll
  for (int j = 0; j < 10; j++) vlo[j] = movm(vlo[j]);
  const bool far0 = 2 * t > g, far1 = 2 * t + 1 > g;
  const uint32_t mfar = (far0 ? 0x0000FFFFu : 0u) | (far1 ? 0xFFFF0000u : 0u);
  float slo[4][2], shi[4][2], lg[2][2];
  uint32_t phi[4], plo[4], qml[4], qmh[4];
#pragma unroll
  for (int h = 0; h < 4; h++) {
    const int f = h == 0 ? 0 : h == 1 ? 3 : h == 2 ? 5 : 8, hf = h < 2 ? 2 : 7;
    const bool mine = (h & 1) ? t >= 2 : t < 2;
    qml[h] = mine ? qlo[hf] : 0u;
    qmh[h] = mine ? qhi[hf] : 0u;
    float a[4] = {0.f, 0.f, 0.f, 0.f}, c[4] = {0.f, 0.f, 0.f, 0.f};
    mma16816(a, qlo[f], qhi[f], qlo[f + 1], qhi[f + 1], klo[f], klo[f + 1]);
    mma16816(c, qlo[f], qhi[f], qlo[f + 1], qhi[f + 1], khi[f], khi[f + 1]);
    mma1688(a, qml[h], qmh[h], klo[hf]);
    mma1688(c, qml[h], qmh[h], khi[hf]);
    slo[h][0] = a[0];
    slo[h][1] = a[1];
    shi[h][0] = lg[h & 1][0] = far0 ? a[2] : c[2];
    shi[h][1] = lg[h & 1][1] = far1 ? a[3] : c[3];
    if (!ATT_MERGE && (h & 1)) softmax_two(lg, phi[h - 1], phi[h]);
  }
  TSIF(par == 0 && w == 1, 65);
  wg_sync(1 + par);
  TSIF(par == 0 && w == 1, 66);
  const bool nohist = (w == 0) && (b < 8);
  const uint4* hp = g_halo + ((b - 8) * 2 + par) * 224 + lane;
  uint32_t tg[7];
  if (w > 0) {
    const uint4 v0 = lds128(xa + (w - 1) * 2560), v1 = lds128(xa + (w - 1) * 2560 + 512), v2 = lds128(xa + (w - 1) * 2560 + 1024);
    const uint4 v3 = lds128(xa + (w - 1) * 2560 + 1536), v4 = lds128(xa + (w - 1) * 2560 + 2048);
    kpv[0] = v0.x; kpv[1] = v0.y; kpv[2] = v0.z; kpv[3] = v0.w; kpv[4] = v1.x; kpv[5] = v1.y; kpv[6] = v1.z; kpv[7] = v1.w;
    kpv[8] = v2.x; kpv[9] = v2.y; vpv[0] = v2.z; vpv[1] = v2.w; vpv[2] = v3.x; vpv[3] = v3.y; vpv[4] = v3.z; vpv[5] = v3.w;
    vpv[6] = v4.x; vpv[7] = v4.y; vpv[8] = v4.z; vpv[9] = v4.w;
  } else if (nohist) {
#pragma unroll
    for (int j = 0; j < 10; j++) kpv[j] = vpv[j] = 0u;
  } else {
    TSIF(par == 0, 77);
    halo_read(kpv, vpv, tg, hp);
  }
  if (w == 0 && !nohist) {
    int spins = 0;
    while (true) {
      bool ok = true;
#pragma unroll
      for (int j = 0; j < 7; j++) ok = ok && tg[j] == tag;
      if (__all_sync(0xffffffffu, ok) || ++spins > SPIN_LIMIT) break;
      halo_read(kpv, vpv, tg, hp);
    }
    TSIF(par == 0, 79);
  }
#pragma unroll
  for (int h = 0; h < 4; h++) {
    const int f = h == 0 ? 0 : h == 1 ? 3 : h == 2 ? 5 : 8, hf = h < 2 ? 2 : 7;
    float a[4] = {0.f, 0.f, 0.f, 0.f};
    mma16816(a, qlo[f], qhi[f], qlo[f + 1], qhi[f + 1], kpv[f], kpv[f + 1]);
    mma1688(a, qml[h], qmh[h], kpv[hf]);
    const float ninf = __int_as_float(0xff800000);
    lg[h & 1][0] = far0 ? (nohist ? ninf : a[0]) : slo[h][0];
    lg[h & 1][1] = far1 ? (nohist ? ninf : a[1]) : slo[h][1];
    if (h & 1) {
      softmax_two(lg, plo[h - 1], plo[h]);
      if (ATT_MERGE) {
        const float lh[2][2] = {{shi[h - 1][0], shi[h - 1][1]}, {shi[h][0], shi[h][1]}};
        softmax_two(lh, phi[h - 1], phi[h]);
      }
    }
  }
  TSIF(par == 0 && w <= 1, 67 + w);
  uint32_t ov[20];
#pragma unroll
  for (int hp = 0; hp < 2; hp++) {
    const int hf = hp ? 7 : 2;
    float sh[4] = {0.f, 0.f, 0.f, 0.f}, i0 = 0.f, i1 = 0.f;
#pragma unroll
    for (int e = 0; e < 2; e++) {
      const int h = 2 * hp + e, f = h == 0 ? 0 : h == 1 ? 3 : h == 2 ? 5 : 8;
      const uint32_t a0 = plo[h] & mfar, a2 = plo[h] & ~mfar, a3 = phi[h] & mfar, c1 = phi[h] & ~mfar;
      float sum[4] = {0.f, 0.f, 0.f, 0.f};
      mma1688(sum, plo[h], phi[h], 0x3F803F80u);
      const float r0 = rcp(sum[0]), r1 = rcp(sum[2]);
#pragma unroll
      for (int j = f; j < f + 2; j++) {
        float o[4] = {0.f, 0.f, 0.f, 0.f};
        mma16816(o, a0, 0u, a2, a3, vpv[j], vlo[j]);
        mma1688(o, 0u, c1, vhi[j]);
        ov[2 * j] = pack2(o[0] * r0, o[1] * r0);
        ov[2 * j + 1] = pack2(o[2] * r1, o[3] * r1);
      }
      const bool mine = e ? g >= 4 : g < 4;
      mma16816(sh, a0, 0u, a2, a3, mine ? vpv[hf] : 0u, mine ? vlo[hf] : 0u);
      mma1688(sh, 0u, c1, mine ? vhi[hf] : 0u);
      if (e == 0 || t >= 2) {
        i0 = r0;
        i1 = r1;
      }
    }
    ov[2 * hf] = pack2(sh[0] * i0, sh[1] * i0);
    ov[2 * hf + 1] = pack2(sh[2] * i1, sh[3] * i1);
  }
  TS(32 + 4 * par + w);
  mbar_wait(sb + OFF_BAR + 8 * B_P1, 0);
  const uint32_t oa = sb + OFF_OA + (lane >> 4) * 2048 + (32 * w + 2 * (lane & 15) + par) * 16;
#pragma unroll
  for (int j = 0; j < 5; j++) stsm4(oa + 4096 * j, ov + 4 * j);
  TSIF(par == 0 && w == 0, 120);
  fence_async_smem();
  TSIF(par == 0 && w == 0, 121);
  __syncwarp();
  if (lane == 0) mbar_arrive(sb + OFF_BAR + 8 * B_ATTN);
  TSM(w == 0 || w == 2, 122 + par + (w == 2 ? 3 : 0));
}

struct Maps {
  CUtensorMap x, wm, wt, k, v, y, wo, qm, qt, om, ot, u;
};

__device__ __forceinline__ void load_stage(uint32_t sb, int kb, int b, const Maps& m) {
  const uint32_t st = sb + (kb & 3) * STAGE_BYTES, bar = sb + OFF_BAR + 8 * (B_FULL1 + (kb & 3));
  const int r = b >> 3, hg = b & 7, slab = kb - KV_KB;
  const bool kv = slab >= 0 && slab < 5;
  const uint32_t kbar = sb + OFF_BAR + 8 * (B_KV + slab), dst = sb + OFF_KVS + slab * KVS_BYTES;
  mbar_expect_tx(bar, STAGE_BYTES);
  if (kv) mbar_expect_tx(kbar, KVS_BYTES);
  tma_3d(st, &m.x, 64 * kb, 64 * r, 0, bar);
  if (kv && KV_MIX) tma_3d(dst, &m.k, 0, 32 * (b >> 1) - 3, 2 * slab + (b & 1), kbar);
  tma_3d(st + ST_W, &m.wm, 80 * hg + (tail_first(hg) ? 16 : 0), 64 * kb, 0, bar);
  if (kv && KV_MIX) tma_3d(dst + KVS_V, &m.v, 0, 32 * (b >> 1), 2 * slab + (b & 1), kbar);
  tma_3d(st + ST_WT, &m.wt, 80 * hg + (tail_first(hg) ? 0 : 64), 64 * kb, 0, bar);
  if (kv && !KV_MIX) tma_3d(dst, &m.k, 0, 32 * (b >> 1) - 3, 2 * slab + (b & 1), kbar);
  if (kv && !KV_MIX) tma_3d(dst + KVS_V, &m.v, 0, 32 * (b >> 1), 2 * slab + (b & 1), kbar);
}

__global__ void __launch_bounds__(NTHR, 1) fused_kernel(const __grid_constant__ Maps m, const Params p) {
  extern __shared__ __align__(1024) uint8_t smem[];
  const uint32_t sb = (uint32_t)__cvta_generic_to_shared(smem);
  const uint32_t bars = sb + OFF_BAR;
  const int tid = threadIdx.x, lane = tid & 31;
  int b = blockIdx.x;
  if (BMAP == 1) b = (((b & 63) >> 3) * 2 + (b & 1)) * 8 + (((b < 64 ? 0x6521 : 0x7430) >> (4 * ((b >> 1) & 3))) & 7);
  if (BMAP == 2) b = ((b & 63) >> 2) * 8 + (((b < 64 ? 0x6521 : 0x7430) >> (4 * (b & 3))) & 7);
  if (BMAP == 3) b = (((b & 63) >> 3) * 2 + (b & 1)) * 8 + (((b < 64 ? 0x7430 : 0x6521) >> (4 * ((b >> 1) & 3))) & 7);
  if (BMAP == 4) b = (((b >> 4) * 2 + (b & 1)) * 8) + ((b >> 1) & 7);
  if (BMAP == 5) b = 127 - b;
  const int r = b >> 3, hg = b & 7;

  if (tid == T_ISSUE) {
    TSM(true, 0);
#pragma unroll
    for (int i = 0; i < 4; i++) mbar_init(bars + 8 * (B_FULL1 + i), 1);
#pragma unroll
    for (int i = 0; i < 3; i++) mbar_init(bars + 8 * (B_KV + i), 1);
    fence_async_smem();
#pragma unroll 1
    for (int kb = 0; kb <= PRE2; kb++) load_stage(sb, kb, b, m);
  } else if (tid >= T_PF && tid < T_PF + 12) {
    tm_prefetch(&m.x + (tid - T_PF));
  } else if (tid == T_INIT) {
#pragma unroll
    for (int i = 0; i < 4; i++) mbar_init(bars + 8 * (B_EMPTY1 + i), 12);
#pragma unroll
    for (int i = 0; i < 8; i++) mbar_init(bars + 8 * (B_FULL2 + i), 1);
#pragma unroll
    for (int i = 0; i < 4; i++) mbar_init(bars + 8 * (B_EMPTY2 + i), 8);
#pragma unroll
    for (int i = 0; i < 4; i++) mbar_init(bars + 8 * (B_U + i), 1);
    mbar_init(bars + 8 * B_HA, 4);
    mbar_init(bars + 8 * B_GATE, 4);
    mbar_init(bars + 8 * B_HB, 1);
    mbar_init(bars + 8 * B_KVD, 4);
    mbar_init(bars + 8 * B_QF, 1);
    mbar_init(bars + 8 * B_ATTN, 8);
    mbar_init(bars + 8 * B_P1, 12);
    mbar_init(bars + 8 * B_C34, 1);
#pragma unroll
    for (int i = 0; i < 5; i++) mbar_init(bars + 8 * (B_YST + i), 4);
#pragma unroll
    for (int i = 0; i < 5; i++) mbar_init(bars + 8 * (B_US + i), 4);
    mbar_init(bars + 8 * B_YSIG, 1);
    mbar_init(bars + 8 * B_YFULL, 1);
    mbar_init(bars + 8 * B_EPOCH, 1);
    mbar_init(bars + 8 * B_PREP, 4);
    mbar_init(bars + 8 * B_USIG, 1);
    mbar_init(bars + 8 * B_WST, 1);
#pragma unroll
    for (int i = 3; i < 5; i++) mbar_init(bars + 8 * (B_KV + i), 1);
    mbar_init(bars + 8 * B_E3, 12);
    mbar_init(bars + 8 * B_LAST, 1);
    mbar_init(bars + 8 * B_OSIG, 1);
    mbar_init(bars + 8 * B_WOP, 1);
    fence_async_smem();
  }
  const int warp = __shfl_sync(0xffffffffu, tid >> 5, 0), wg = warp >> 2, w = warp & 3;
  __syncthreads();

  if (wg == 3) {
    asm volatile("setmaxnreg.dec.sync.aligned.u32 56;");
    if (w == 0) {
      if (lane == 0) {
#pragma unroll 1
        for (int kb = 1 + PRE2; kb < 10; kb++) {
          if (kb >= 4) mbar_wait(bars + 8 * (kb == 7 ? B_E3 : B_EMPTY1 + (kb & 3)), (kb >> 3) & 1);
          TSIF(kb >= 4, 44 + kb);
          load_stage(sb, kb, b, m);
          TSIF(kb == 3, 60);
          if (kb == TRIG_KB) mbar_arrive(bars + 8 * B_LAST);
        }
        mbar_wait(bars + 8 * B_WOP, 0);
        mbar_wait(bars + 8 * WL_TRIG, 0);
        mbar_wait(bars + 8 * B_EPOCH, 0);
        flag_wait(g_cnt + C_W + 32 * hg, (lds32(sb + OFF_EPOCH) + 1) * 16);
        TS(30);
#pragma unroll 1
        for (int j = 0; j < 8; j++) {
          if (j >= 6) mbar_wait(bars + 8 * (B_EMPTY2 + j - 6), 0);
          if (j == 4) mbar_wait(bars + 8 * B_ATTN, 0);
          TSIF(j >= 6, 100 + j);
          if (RF_GATE && j == 6) mbar_wait(bars + 8 * B_YSIG, 0);
          mbar_expect_tx(bars + 8 * (B_FULL2 + j), j == 0 ? WO_BYTES : j == 5 ? O_BYTES + WO_BYTES + 512 : O_BYTES + WO_BYTES);
          bulk_load(sb + off_w(j), g_WO + (hg * 8 + step_src(hg, j)) * 800, WO_BYTES, bars + 8 * (B_FULL2 + j));
        }
        mbar_wait(bars + 8 * (B_EMPTY2 + 3), 0);
        mbar_expect_tx(bars + 8 * B_QF, O_BYTES);
        tma_2d(sb + OFF_QS, &m.qm, 80 * hg, 128 * r, bars + 8 * B_QF);
        tma_2d(sb + OFF_QT, &m.qt, 80 * hg + 64, 128 * r, bars + 8 * B_QF);
      }
    } else if (w == 1) {
      unsigned epoch = 0;
      if (lane == 0) {
        epoch = atomicAdd(g_cnt + C_LAUNCH, 1u) / NCTA;
        asm volatile("st.shared.u32 [%0], %1;" ::"r"(sb + OFF_EPOCH), "r"(epoch) : "memory");
        mbar_arrive(bars + 8 * B_EPOCH);
        mbar_wait(bars + 8 * B_KVD, 0);
        mbar_expect_tx(bars + 8 * B_HB, 5 * 4096);
#pragma unroll 1
        for (int c = 0; c < 5; c++) {
          if (c == 3) mbar_wait(bars + 8 * B_S3, 0);
          bulk_load(sb + off_ch(c) + U_BYTES, p.ssm_k + (5 * b + c) * SEQ, 4096, bars + 8 * B_HB);
        }
#pragma unroll
        for (int c = 0; c < 4; c++) mbar_expect_tx(bars + 8 * (B_U + c), c < 3 ? U_BYTES : 2 * U_BYTES);
        const uint4* usrc = g_U + 5 * b * U_PITCH;
        mbar_wait(bars + 8 * B_USIG, 0);
        flag_wait(g_cnt + C_PREP + 32 * (b & 15), (epoch + 1) * NCTA);
        TS(23);
#pragma unroll
        for (int c = 0; c < 5; c++) {
          if (c == 3) mbar_wait(bars + 8 * (B_U + 2), 0);
          bulk_load(sb + off_ch(c), usrc + c * U_PITCH, U_BYTES, bars + 8 * (B_U + (c < 3 ? c : 3)));
          TSIF(c == 0 || c == 4, 116 + (c >> 2));
        }
      }
      epoch = __shfl_sync(0xffffffffu, epoch, 0);
      if (lane < 8) {
        const int src = (b & ~7) | step_src(hg, lane);
        mbar_wait(bars + 8 * B_OSIG, 0);
        TS(20);
        flag_wait(g_cnt + C_O + 32 * src, epoch + 1);
        if (lane >= 1 && lane < 4) bulk_load(sb + off_o(lane), g_O + src * 1280, O_BYTES, bars + 8 * (B_FULL2 + lane));
        __syncwarp(0xff);
        TS(21);
        if (lane == 5) bulk_load(sb + OFF_GATE, g_gate + 128 * r, 512, bars + 8 * (B_FULL2 + 5));
#pragma unroll 1
        for (int j = 4; j < 8; j++) {
          if (lane == j) {
            mbar_wait(bars + 8 * (j < 6 ? B_C34 : B_EMPTY2 + j - 6), 0);
            if (RF_GATE && j == 6) mbar_wait(bars + 8 * B_YSIG, 0);
            bulk_load(sb + off_o(j), g_O + src * 1280, O_BYTES, bars + 8 * (B_FULL2 + j));
          }
          __syncwarp(0xff);
        }
        TS(22);
      }
    } else if (w == 2) {
      mbar_wait(bars + 8 * B_PREP, 0);
      flag_signal(g_cnt + C_PREP, 16, lane);
      TS(25);
      if (lane == 0) mbar_arrive(bars + 8 * B_USIG);
      mbar_wait(bars + 8 * B_GATE, 0);
      if ((NOMB & 1) && lane == 0) asm volatile("fence.release.gpu;" ::: "memory");
      mbar_wait(bars + 8 * B_ATTN, 0);
      if (lane == 0) {
        if (O_DEFER) mbar_wait(bars + 8 * (B_U + 3), 0);
        asm volatile("cp.async.bulk.global.shared::cta.bulk_group [%0], [%1], 20480;\ncp.async.bulk.commit_group;\n"
                     "cp.async.bulk.wait_group 0;\nfence.proxy.async.global;" ::"l"(g_O + b * 1280), "r"(sb + OFF_OA) : "memory");
      }
      TS(74);
      if (!(NOMB & 1)) flag_signal(g_cnt + C_O + 32 * b, 1, lane);
      else if (lane == 0) flag_bump(g_cnt + C_O + 32 * b);
      TS(26);
      if (lane == 0) mbar_arrive(bars + 8 * B_OSIG);

    } else {
      if (lane == 0) {
        uint4* dst = g_WO + (hg * 8 + (r >> 1)) * 800 + (r & 1) * 80;
        mbar_wait(bars + 8 * B_P1, 0);
        mbar_wait(bars + 8 * WB_TRIG, 0);
        mbar_expect_tx(bars + 8 * B_WST, WO_BYTES / 2);
        tma_3d(sb + OFF_WS, &m.wo, 0, 40 * r, 5 * hg, bars + 8 * B_WST);
        mbar_wait(bars + 8 * B_WST, 0);
        mbar_wait(bars + 8 * WO_TRIG, 0);
#pragma unroll 1
        for (int n = 0; n < 5; n++)
          asm volatile("cp.async.bulk.global.shared::cta.bulk_group [%0], [%1], 1280;" ::"l"(dst + 160 * n), "r"(sb + OFF_WS + 1280 * n) : "memory");
        asm volatile("cp.async.bulk.commit_group;\ncp.async.bulk.wait_group 0;\nfence.proxy.async.global;" ::: "memory");
        if (!(NOMB & 4)) asm volatile("fence.release.gpu;" ::: "memory");
        flag_bump(g_cnt + C_W + 32 * hg);
        mbar_arrive(bars + 8 * B_WOP);
        TS(71);
#pragma unroll 1
        for (int c = 0; c < 5; c++) {
          mbar_wait(bars + 8 * (B_YST + c), 0);
          asm volatile("cp.async.bulk.global.shared::cta.bulk_group [%0], [%1], 4096;\ncp.async.bulk.commit_group;"
                       ::"l"(g_Y + (5 * b + c) * Y_PITCH), "r"(sb + off_ch(c)) : "memory");
          if (c == 2) {
            asm volatile("cp.async.bulk.wait_group.read 0;" ::: "memory");
            mbar_arrive(bars + 8 * B_C34);
          }
        }
        asm volatile("cp.async.bulk.wait_group 0;\nfence.proxy.async.global;" ::: "memory");
        TS(75);
        if (!(NOMB & 2)) asm volatile("fence.release.gpu;" ::: "memory");
        flag_bump(g_cnt + C_Y + 32 * (b >> 4));
        TS(27);
        mbar_arrive(bars + 8 * B_YSIG);
        mbar_expect_tx(bars + 8 * B_YFULL, 20480);
        flag_wait(g_cnt + C_Y + 32 * hg, (lds32(sb + OFF_EPOCH) + 1) * 16);
        TS(24);
        tma_2d(sb + OFF_YT, &m.y, 128 * r, 80 * hg, bars + 8 * B_YFULL);
        tma_2d(sb + OFF_YT + 10240, &m.y, 128 * r + 64, 80 * hg, bars + 8 * B_YFULL);
      }
    }
  } else {
    asm volatile("setmaxnreg.inc.sync.aligned.u32 152;");
    if (wg < 2) {
      float acc[120];
#pragma unroll
      for (int i = 0; i < 120; i++) acc[i] = 0.f;
      const uint32_t da = desc_lo(sb + wg * 8192, 16), db = desc_lo(sb + ST_W, 8192), dc = desc_lo(sb + ST_WT, 2048);
      if (PW1) pin<120>(acc);
      if (PW1 == 2) mbar_wait(bars + 8 * B_FULL1, 0);
#pragma unroll 1
      for (int kb = 0; kb < 10; kb++) {
        mbar_wait(bars + 8 * (B_FULL1 + (kb & 3)), (kb >> 2) & 1);
        const uint32_t so = (kb & 3) * (STAGE_BYTES >> 4);
        wg_fence();
#pragma unroll
        for (int k = 0; k < 4; k++) {
          WgSST<192>::mma<HI_SW128, HI_SW128>(acc, da + so + 2 * k, db + so + 128 * k, 1);
          WgSST<48>::mma<HI_SW128, HI_SW32>(acc + 96, da + so + 2 * k, dc + so + 32 * k, 1);
        }
        wg_commit();
        wg_wait<1>();
        if (kb > 0 && lane == 0) mbar_arrive(bars + 8 * (kb == 4 ? B_E3 : B_EMPTY1 + ((kb - 1) & 3)));
      }
      mbar_wait(bars + 8 * B_EPOCH, 0);
      const uint32_t tag = lds32(sb + OFF_EPOCH) + 1;
      mbar_wait(bars + 8 * B_S3, 0);
      wg_wait<0>();
      pin<120>(acc);
      if (lane == 0) mbar_arrive(bars + 8 * B_P1);
      TSM(w == 0, 3 + wg);
      attention(acc, sb, b, wg, w, lane, tag);
    } else {
      const int tw = tid & 127, chl = 64 * (b & 1) + 8 * w + (lane >> 2);
      uint4* up = g_U + chl * U_PITCH + ((4 * (b >> 1) + (lane & 3)) ^ ((b >> 2) & 1));
      uint2 sw[10];
      uint32_t dv = 0;
      if (lane < 5) dv = __ldg(reinterpret_cast<const unsigned short*>(p.ssm_D) + 5 * b + lane);
#pragma unroll
      for (int i = 0; i < 10; i++) sw[i] = ldg64(reinterpret_cast<const uint2*>(p.shift_k) + chl + 128 * (i >> 1) + 32 * (i & 1));
      uint32_t tab[12];
      float tt[4];
      fft_tables(tab, tw);
      fft_twiddles(tt, tw);
      uint4 res[10];
#pragma unroll
      for (int i = 0; i < 10; i++) res[i] = make_uint4(0, 0, 0, 0);
      const int gi = 8 * hg + (tw >> 4);
      const uint32_t xa = sb + ((tw >> 3) & 1) * 8192 + gi * 128 + (((tw ^ gi) & 7) << 4);
      uint4 gw = ldg128(reinterpret_cast<const uint4*>(p.gate_w) + (lane & 7));
      float z = 0.f;
#pragma unroll 1
      for (int kb = 0; kb < KV_KB + 5; kb++) {
        gate_step(z, gw, p, sb, xa, kb, lane);
        const int slab = kb - KV_KB;
        if (slab < 0) continue;
#pragma unroll
        for (int i = 0; i < 8; i++) res[i] = res[i + 2];
        prep_slab(res + 8, sw, sb, slab, w, lane);
        TSIF(w == 0, 99 + 4 * slab);
#pragma unroll
        for (int i = 0; i < 8; i++) sw[i] = sw[i + 2];
      }
      TSIF(w == 0, 28);
      __syncwarp();
      if (lane == 0) mbar_arrive(bars + 8 * B_KVD + ((res[8].x ^ res[9].x) & p.zero));
#pragma unroll 1
      for (int kb = KV_KB + 5; kb < 8; kb++) gate_step(z, gw, p, sb, xa, kb, lane);
      mbar_wait(bars + 8 * B_KVD, 0);
      fft_tables_store(tab, sb, tw);
      mbar_wait(bars + 8 * B_LAST, 0);
#pragma unroll
      for (int i = 0; i < 10; i++) up[(128 * (i >> 1) + 32 * (i & 1)) * U_PITCH] = res[i];
      __syncwarp();
      if (lane == 0) mbar_arrive(bars + 8 * B_PREP);
      TSIF(w == 0 && !U_TMA, 5);
#pragma unroll 1
      for (int kb = 8; kb < 10; kb++) gate_step(z, gw, p, sb, xa, kb, lane);
#pragma unroll
      for (int o = 4; o > 0; o >>= 1) z += __shfl_xor_sync(0xffffffffu, z, o);
      z = bf_lo(pack2(z, 0.f));
      if ((lane & 7) == 0) g_gate[16 * b + (tw >> 3)] = bf_lo(pack2(__fdividef(1.f, 1.f + __expf(-z)), 0.f));
      __syncwarp();
      if (lane == 0) mbar_arrive(bars + 8 * B_GATE);
      TSIF(w == 0, 72);
      mbar_wait(bars + 8 * B_HB, 0);
      TSIF(w == 0, 2);
      const uint32_t ha = sb + U_BYTES + ((tw >> 3) * 16 + 8 + (tw & 7)) * 16;
      uint4 hv[5];
#pragma unroll
      for (int c = 0; c < 5; c++) hv[c] = lds128(ha + off_ch(c));
      __syncwarp();
#pragma unroll
      for (int c = 0; c < 5; c++) sts128((ha ^ 16) + off_ch(c), hv[c].x, hv[c].y, hv[c].z, hv[c].w);
      sts128(sb + OFF_TT + 16 * tw, __float_as_uint(tt[0]), __float_as_uint(tt[1]), __float_as_uint(tt[2]), __float_as_uint(tt[3]));
      if (tw < 5) asm volatile("st.shared.f32 [%0], %1;" ::"r"(sb + OFF_D + 4 * tw), "f"(bf_lo(dv) * 0.125f) : "memory");
      fence_async_smem();
      __syncwarp();
      if (lane == 0) mbar_arrive(bars + 8 * B_HA);
      TSIF(w == 0, 6);
    }

    FftConst fc;
    TSM(w == 0 && wg == 0, 104);
    mbar_wait(bars + 8 * B_HA, 0);
    fft_matrices(fc, sb, w, lane);
    TSM(w == 0 && wg == 0, 105);
    if (ATT_GATE && !H_EARLY) mbar_wait(bars + 8 * B_ATTN, 0);
    TSM(w == 0 && wg == 2, 124);
#pragma unroll 1
    for (uint32_t tasks = wg == 0 ? TASK0 : wg == 1 ? TASK1 : TASK2; tasks; tasks >>= 4) {
      const int c = (tasks & 7) - 1;
      conv_channel(fc, sb, c, wg, w, lane);
      if (lane == 0) mbar_arrive(bars + 8 * (B_YST + c));
      TSM(w == 0, 10 + c);
    }

    if (wg < 2) {
      const int g = lane >> 2;
      float acc[40];
#pragma unroll
      for (int i = 0; i < 40; i++) acc[i] = 0.f;
      const uint32_t da = desc_lo(sb + wg * 1024, 2048), db = desc_lo(sb, 2560);
      mbar_wait(bars + 8 * B_ATTN, 0);
      mbar_wait(bars + 8 * (B_YST + 3), 0);
      mbar_wait(bars + 8 * (B_YST + 4), 0);
      if (PW2) mbar_wait(bars + 8 * B_FULL2, 0);
      TSM(w == 0, 15 + wg);
#pragma unroll 1
      for (int j = 0; j < 8; j++) {
        mbar_wait(bars + 8 * (B_FULL2 + j), 0);
        const uint32_t oa = da + (off_o(j) >> 4), ob = db + (off_w(j) >> 4);
        wg_fence();
#pragma unroll
        for (int k = 0; k < 5; k++) WgSST<80>::mma<HI_NONE, HI_SW32>(acc, oa + 256 * k, ob + 32 * k, 1);
        wg_commit();
        wg_wait<1>();
        if (j >= 1 && j <= 4 && lane == 0) mbar_arrive(bars + 8 * (B_EMPTY2 + j - 1));
      }
      TSIF(w == 0 && wg == 0, 113);
      const int tr = 64 * wg + 16 * w + (lane & 15);
      const uint32_t fm = sb + OFF_QS + tr * 128, fx = (lane >> 4) ^ (tr & 7);
      const uint32_t ft = sb + OFF_QT + tr * 32 + (((lane >> 4) ^ (tr >> 2)) & 1) * 16;
      const float g0 = __uint_as_float(lds32(sb + OFF_GATE + (64 * wg + 16 * w + g) * 4));
      const float g1 = __uint_as_float(lds32(sb + OFF_GATE + (64 * wg + 16 * w + 8 + g) * 4));
      const uint32_t ga = pack2(g0, g0), gb = pack2(g1, g1);
      const uint32_t na = pack2(1.f - g0, 1.f - g0), nb = pack2(1.f - g1, 1.f - g1);

      wg_wait<0>();
      pin<40>(acc);
      TSM(w == 0, 17 + wg);
      uint32_t pb[20];
#pragma unroll
      for (int j = 0; j < 10; j++) {
        pb[2 * j] = bmul(na, pack2(acc[4 * j], acc[4 * j + 1]));
        pb[2 * j + 1] = bmul(nb, pack2(acc[4 * j + 2], acc[4 * j + 3]));
        asm volatile("" : "+r"(pb[2 * j]), "+r"(pb[2 * j + 1]));
      }
      const uint32_t ya = sb + OFF_YT + wg * 10240 + ((lane >> 4) * 8 + (lane & 7)) * 128 +
                          (((2 * w + (((lane >> 3) & 1) ^ wg)) ^ (lane & 7)) << 4);
      uint32_t qf[20];
      mbar_wait(bars + 8 * B_QF, 0);
#pragma unroll
      for (int j = 0; j < 5; j++) ldsm4(qf + 4 * j, j < 4 ? fm + ((fx ^ (2 * j)) << 4) : ft);
      mbar_wait(bars + 8 * B_YFULL, 0);
      TSM(w == 0 && wg == 0, 19);
#pragma unroll
      for (int j = 0; j < 5; j++) {
        uint32_t y[4];
        ldsm4t(y, ya + 2048 * j);
#pragma unroll
        for (int i = 0; i < 4; i++) qf[4 * j + i] = badd(bmul((i & 1) ? gb : ga, bmul(qf[4 * j + i], y[i])), pb[4 * j + i]);
      }
#pragma unroll
      for (int j = 0; j < 5; j++) stsm4(j < 4 ? fm + ((fx ^ (2 * j)) << 4) : ft, qf + 4 * j);
      fence_async_smem();
      __syncwarp();
      if (lane == 0) {
        const int row = 64 * wg + 16 * w;
        asm volatile("cp.async.bulk.tensor.2d.global.shared::cta.bulk_group [%0, {%2, %3}], [%1];"
                     ::"l"(&m.om), "r"(sb + OFF_QS + row * 128), "r"(80 * hg), "r"(128 * r + row) : "memory");
        asm volatile("cp.async.bulk.tensor.2d.global.shared::cta.bulk_group [%0, {%2, %3}], [%1];"
                     ::"l"(&m.ot), "r"(sb + OFF_QT + row * 32), "r"(80 * hg + 64), "r"(128 * r + row) : "memory");
        asm volatile("cp.async.bulk.commit_group;\ncp.async.bulk.wait_group.read 0;" ::: "memory");
      }
      TSM(true, 40 + 4 * wg + w);
      if (ENDBAR) asm volatile("bar.sync 15, 256;" ::: "memory");
    }
  }
}

typedef CUresult (*EncodeFn)(CUtensorMap*, CUtensorMapDataType, cuuint32_t, void*, const cuuint64_t*, const cuuint64_t*,
                             const cuuint32_t*, const cuuint32_t*, CUtensorMapInterleave, CUtensorMapSwizzle,
                             CUtensorMapL2promotion, CUtensorMapFloatOOBfill);

void encode(EncodeFn fn, CUtensorMap* tm, const void* base, int rank, const cuuint64_t* dims, const cuuint64_t* strides,
            const cuuint32_t* box, CUtensorMapSwizzle swz) {
  const cuuint32_t ones[3] = {1, 1, 1};
  fn(tm, CU_TENSOR_MAP_DATA_TYPE_BFLOAT16, rank, const_cast<void*>(base), dims, strides, box, ones,
     CU_TENSOR_MAP_INTERLEAVE_NONE, swz, CU_TENSOR_MAP_L2_PROMOTION_L2_128B, CU_TENSOR_MAP_FLOAT_OOB_FILL_NONE);
}

}

extern "C" void kernel_launch(void* const* d_in, const int* in_sizes, int n_in, void* d_out, int out_size) {
  (void)in_sizes; (void)n_in; (void)out_size;
  Params p;
  p.q = (const __nv_bfloat16*)d_in[0];
  p.k = (const __nv_bfloat16*)d_in[1];
  p.v = (const __nv_bfloat16*)d_in[2];
  p.shift_k = (const __nv_bfloat16*)d_in[3];
  p.ssm_k = (const __nv_bfloat16*)d_in[4];
  p.ssm_D = (const __nv_bfloat16*)d_in[5];
  p.wqkv = (const __nv_bfloat16*)d_in[7];
  p.wo = (const __nv_bfloat16*)d_in[8];
  p.gate_w = (const __nv_bfloat16*)d_in[9];
  p.out = (__nv_bfloat16*)d_out;
  p.zero = 0;

  static EncodeFn fn = nullptr;
  static void *yaddr = nullptr, *uaddr = nullptr;
  if (!fn) {
    cudaDriverEntryPointQueryResult qr;
    void* f = nullptr;
    cudaGetDriverEntryPoint("cuTensorMapEncodeTiled", &f, cudaEnableDefault, &qr);
    fn = (EncodeFn)f;
    cudaGetSymbolAddress(&yaddr, g_Y);
    cudaGetSymbolAddress(&uaddr, g_U);
    cudaFuncSetAttribute(fused_kernel, cudaFuncAttributeMaxDynamicSharedMemorySize, SMEM_BYTES);
  }
  Maps m;
  {
    const cuuint64_t dims[3] = {640, 1024, 2}, st[2] = {2560, 1280};
    const cuuint32_t box[3] = {64, 64, 2};
    encode(fn, &m.x, p.q, 3, dims, st, box, CU_TENSOR_MAP_SWIZZLE_128B);
  }
  {
    const cuuint64_t dims[3] = {640, 640, 3}, st[2] = {3840, 1280};
    const cuuint32_t box[3] = {64, 64, 3}, boxt[3] = {16, 64, 3};
    encode(fn, &m.wm, p.wqkv, 3, dims, st, box, CU_TENSOR_MAP_SWIZZLE_128B);
    encode(fn, &m.wt, p.wqkv, 3, dims, st, boxt, CU_TENSOR_MAP_SWIZZLE_32B);
  }
  {
    const cuuint64_t dims[3] = {64, 2048, 10}, st[2] = {1280, 128};
    const cuuint32_t boxk[3] = {64, 35, 1}, boxv[3] = {64, 32, 1};
    encode(fn, &m.k, p.k, 3, dims, st, boxk, CU_TENSOR_MAP_SWIZZLE_128B);
    encode(fn, &m.v, p.v, 3, dims, st, boxv, CU_TENSOR_MAP_SWIZZLE_128B);
  }
  {
    const cuuint64_t dims[3] = {16, 640, 40}, st[2] = {1280, 32};
    const cuuint32_t box[3] = {16, 40, 5};
    encode(fn, &m.wo, p.wo, 3, dims, st, box, CU_TENSOR_MAP_SWIZZLE_32B);
  }
  {
    const cuuint64_t dims[2] = {2048, 640}, st[1] = {Y_PITCH * 16};
    const cuuint32_t box[2] = {64, 80};
    encode(fn, &m.y, yaddr, 2, dims, st, box, CU_TENSOR_MAP_SWIZZLE_128B);
    const cuuint64_t stu[1] = {U_PITCH * 16};
    const cuuint32_t boxu[2] = {32, 64};
    encode(fn, &m.u, uaddr, 2, dims, stu, boxu, CU_TENSOR_MAP_SWIZZLE_NONE);
  }
  {
    const cuuint64_t dims[2] = {640, 2048}, st[1] = {1280};
    const cuuint32_t bqm[2] = {64, 128}, bqt[2] = {16, 128}, bom[2] = {64, 16}, bot[2] = {16, 16};
    encode(fn, &m.qm, p.q, 2, dims, st, bqm, CU_TENSOR_MAP_SWIZZLE_128B);
    encode(fn, &m.qt, p.q, 2, dims, st, bqt, CU_TENSOR_MAP_SWIZZLE_32B);
    encode(fn, &m.om, p.out, 2, dims, st, bom, CU_TENSOR_MAP_SWIZZLE_128B);
    encode(fn, &m.ot, p.out, 2, dims, st, bot, CU_TENSOR_MAP_SWIZZLE_32B);
  }
  fused_kernel<<<NCTA, NTHR, SMEM_BYTES>>>(m, p);
}
```

```cpp
#include <cuda.h>
#include <cuda_bf16.h>
#include <cuda_runtime.h>
#include <stdint.h>

namespace {

constexpr int SEQ = 2048, DIM = 640, NCTA = 128, NTHR = 512;

#define TRIG_KB 9
#define KV_KB 2
#define DEV_EXIT 0
#define ATT_GATE 1
#define FENCE_LO 0
#define FENCE_HI 0
#define PW1 2
#define PW2 1
#define ENDBAR 0
#define PAD_KB 0
#define Y_ALIAS 1
#define H_EARLY 1
#define NOMB 0
#define SRC_ROT 0
#define WAIT_NS 0
#define WB_TRIG B_USIG
#define TAILF 1
#define T_ISSUE 384
#define T_PF 416
#define T_INIT 448
#define ATT_MERGE 0
#define BMAP 1
#define PRE2 1
#define KV_MIX 0
#define O_DEFER 0
#define TASK0 0x52
#define TASK1 0x3
#define TASK2 0x41
#define HALO_FIRST 1
#define PREV_EARLY 0
#define ACQ 0
#define U_TMA 0
#define U_GATE 0
#define RF_GATE 0
#define WO_TRIG B_WST
#define WL_TRIG B_WOP
#define WO_GATE 1

constexpr uint32_t STAGE_BYTES = 47104, ST_W = 16384, ST_WT = 40960;
constexpr uint32_t O_BYTES = 20480, WO_BYTES = 12800;
constexpr uint32_t OFF_OA = 0;
constexpr uint32_t OFF_QS = 3 * O_BYTES, OFF_QT = OFF_QS + 16384;
constexpr uint32_t OFF_WC = 81920;
constexpr uint32_t OFF_WA = 94720;
constexpr uint32_t OFF_GATE = 145920;
constexpr uint32_t OFF_TT = 146432;
constexpr uint32_t OFF_KVX = 148480;
constexpr uint32_t OFF_CH3 = 163840;
constexpr uint32_t CH_BYTES = 12288, U_BYTES = 4096;
constexpr uint32_t OFF_FT = 225280, OFF_GT = 229376;
constexpr uint32_t OFF_CH0 = 188416;
constexpr uint32_t OFF_KVS = OFF_CH0, KVS_V = 4480, KVS_BYTES = 8576;
constexpr uint32_t OFF_WS = OFF_WA;
__device__ __forceinline__ uint32_t off_us(int s) { return OFF_CH0 + 4096 * ((0x65320 >> (4 * s)) & 7); }
constexpr uint32_t OFF_YT = 163840;
constexpr uint32_t OFF_BAR = 231936;
constexpr uint32_t SMEM_BYTES = OFF_BAR + 512;

enum : uint32_t {
  B_FULL1 = 0, B_EMPTY1 = 4, B_S3 = 7, B_FULL2 = 52, B_EMPTY2 = 13, B_U = 8, B_GATE = 12, B_HA = 19, B_HB = 20,
  B_ATTN = 21, B_C34 = 22, B_CONV = 23, B_YFULL = 24, B_EPOCH = 25, B_PREP = 26, B_P1 = 27, B_LAST = 28,
  B_E3 = 29, B_OSIG = 30, B_WOP = 31, B_USIG = 32, B_WST = 33, B_KV = 34, B_KVD = 39, B_QF = 17, B_YST = 40,
  B_US = 45, B_YSIG = 50
};
constexpr uint32_t OFF_EPOCH = OFF_BAR + 8 * 51, OFF_D = OFF_BAR + 8 * 60;
__device__ __forceinline__ uint32_t off_o(int j) { return j < 4 ? OFF_OA + j * O_BYTES : j < 6 ? OFF_CH0 + (j - 4) * O_BYTES : OFF_OA + (j - 6) * O_BYTES; }
__device__ __forceinline__ uint32_t off_w(int j) { return j < 4 ? OFF_WA + j * WO_BYTES : j == 4 ? OFF_KVX : j == 5 ? OFF_WC : OFF_WA + (j - 6) * WO_BYTES; }
__device__ __forceinline__ int step_src(int hg, int j) { return SRC_ROT ? (hg + j) & 7 : j == 0 ? hg : j <= hg ? j - 1 : j; }
__device__ __forceinline__ bool tail_first(int hg) { return TAILF && (hg & 3) == 3; }
__device__ __forceinline__ uint32_t off_ch(int c) { return (c < 3 ? OFF_CH0 : OFF_CH3 - 3 * CH_BYTES) + c * CH_BYTES; }

#define U_PITCH 264
__device__ __align__(1024) uint4 g_U[DIM * U_PITCH];
__device__ uint4 g_O[NCTA * 1280];
#define g_Y g_U
constexpr int Y_PITCH = U_PITCH;
__device__ uint4 g_WO[64 * 800];
__device__ uint4 g_halo[NCTA * 2 * 7 * 32];
__device__ float g_gate[SEQ + PAD_KB * 256];
__device__ unsigned g_cnt[32 * (1 + 2 * 16 + 8 + NCTA)];
constexpr int C_LAUNCH = 0, C_PREP = 32, C_Y = 32 * 17, C_W = 32 * 33, C_O = 32 * 41;

#define TSM(cond, slot) do { } while (0)
#define TSIF(cond, slot) do { if (__LINE__ >= FENCE_LO && __LINE__ < FENCE_HI) sched_fence(); } while (0)
__device__ __forceinline__ void sched_fence() {
  asm volatile("{\n.reg .pred p;\n.reg .u32 c;\nmov.u32 c, %%clock;\nsetp.eq.u32 p, c, 0;\n@p st.shared.u32 [%0], c;\n}"
               ::"r"(1024 + OFF_EPOCH + 4) : "memory");
}
#define TS(slot) TSIF(true, slot)

struct Params {
  const __nv_bfloat16 *q, *k, *v, *shift_k, *ssm_k, *ssm_D, *wqkv, *wo, *gate_w;
  __nv_bfloat16* out;
  uint32_t zero;
};

#define POLL_NS 0
constexpr int SPIN_LIMIT = 1 << 17;

__device__ __forceinline__ void mbar_init(uint32_t bar, uint32_t count) {
  asm volatile("mbarrier.init.shared::cta.b64 [%0], %1;" ::"r"(bar), "r"(count) : "memory");
}
__device__ __forceinline__ void mbar_expect_tx(uint32_t bar, uint32_t bytes) {
  asm volatile("mbarrier.arrive.expect_tx.shared::cta.b64 _, [%0], %1;" ::"r"(bar), "r"(bytes) : "memory");
}
__device__ __forceinline__ void mbar_arrive(uint32_t bar) {
  asm volatile("mbarrier.arrive.shared::cta.b64 _, [%0];" ::"r"(bar) : "memory");
}
__device__ __forceinline__ void mbar_wait(uint32_t bar, uint32_t parity) {
  uint32_t ok;
  int spins = 0;
  do {
    if (WAIT_NS)
      asm volatile("{\n.reg .pred p;\nmbarrier.try_wait.parity.shared::cta.b64 p, [%1], %2, %3;\nselp.b32 %0, 1, 0, p;\n}"
                   : "=r"(ok) : "r"(bar), "r"(parity), "r"(WAIT_NS) : "memory");
    else
      asm volatile("{\n.reg .pred p;\nmbarrier.try_wait.parity.shared::cta.b64 p, [%1], %2;\nselp.b32 %0, 1, 0, p;\n}"
                   : "=r"(ok) : "r"(bar), "r"(parity) : "memory");
    if (++spins > SPIN_LIMIT) break;
  } while (!ok);
}
__device__ __forceinline__ unsigned flag_read(const unsigned* p) {
  unsigned v;
  asm volatile("ld.relaxed.gpu.global.u32 %0, [%1];" : "=r"(v) : "l"(p) : "memory");
  return v;
}
__device__ __forceinline__ void flag_poll(const unsigned* p, unsigned target) {
  unsigned v;
  int spins = 0;
  do {
    if (POLL_NS && spins) __nanosleep(POLL_NS);
    asm volatile("ld.relaxed.gpu.global.u32 %0, [%1];" : "=r"(v) : "l"(p) : "memory");
    if (++spins > SPIN_LIMIT) break;
  } while ((int)(v - target) < 0);
}
__device__ __forceinline__ void flag_wait(const unsigned* p, unsigned target) {
  flag_poll(p, target);
  if (ACQ) asm volatile("fence.acquire.gpu;\nfence.proxy.async.global;" ::: "memory");
}
__device__ __forceinline__ void flag_signal(unsigned* p, int n, int lane) {
  if (lane == 0) asm volatile("fence.release.gpu;" ::: "memory");
  __syncwarp();
  if (lane < n) asm volatile("red.relaxed.gpu.global.add.u32 [%0], 1;" ::"l"(p + 32 * lane) : "memory");
}
__device__ __forceinline__ void flag_bump(unsigned* p) {
  asm volatile("red.relaxed.gpu.global.add.u32 [%0], 1;" ::"l"(p) : "memory");
}
__device__ __forceinline__ void fence_async_smem() { asm volatile("fence.proxy.async.shared::cta;" ::: "memory"); }
__device__ __forceinline__ void wg_sync(int id) { asm volatile("bar.sync %0, 128;" ::"r"(id) : "memory"); }

__device__ __forceinline__ void tma_2d(uint32_t dst, const CUtensorMap* tm, int c0, int c1, uint32_t bar) {
  asm volatile("cp.async.bulk.tensor.2d.shared::cluster.global.mbarrier::complete_tx::bytes [%0], [%1, {%3, %4}], [%2];"
               ::"r"(dst), "l"(tm), "r"(bar), "r"(c0), "r"(c1) : "memory");
}
__device__ __forceinline__ void tma_3d(uint32_t dst, const CUtensorMap* tm, int c0, int c1, int c2, uint32_t bar) {
  asm volatile("cp.async.bulk.tensor.3d.shared::cluster.global.mbarrier::complete_tx::bytes [%0], [%1, {%3, %4, %5}], [%2];"
               ::"r"(dst), "l"(tm), "r"(bar), "r"(c0), "r"(c1), "r"(c2) : "memory");
}
__device__ __forceinline__ void bulk_load(uint32_t dst, const void* src, uint32_t bytes, uint32_t bar) {
  asm volatile("cp.async.bulk.shared::cluster.global.mbarrier::complete_tx::bytes [%0], [%1], %2, [%3];"
               ::"r"(dst), "l"(src), "r"(bytes), "r"(bar) : "memory");
}
__device__ __forceinline__ void tm_prefetch(const CUtensorMap* tm) {
  asm volatile("prefetch.tensormap [%0];" ::"l"(tm) : "memory");
}

__device__ __forceinline__ void wg_fence() { asm volatile("wgmma.fence.sync.aligned;" ::: "memory"); }
__device__ __forceinline__ void wg_commit() { asm volatile("wgmma.commit_group.sync.aligned;" ::: "memory"); }
template <int N> __device__ __forceinline__ void wg_wait() { asm volatile("wgmma.wait_group.sync.aligned %0;" ::"n"(N) : "memory"); }
__device__ __forceinline__ uint32_t desc_lo(uint32_t addr, uint32_t lbo) { return ((addr & 0x3FFFF) >> 4) | ((lbo >> 4) << 16); }
constexpr uint32_t desc_hi(uint32_t sbo, uint32_t swz) { return (sbo >> 4) | (swz << 30); }
constexpr uint32_t HI_SW128 = desc_hi(1024, 1), HI_SW64 = desc_hi(512, 2), HI_SW32 = desc_hi(256, 3), HI_NONE = desc_hi(128, 0);
template <int N> __device__ __forceinline__ void pin(float* d) {
#pragma unroll
  for (int i = 0; i < N; i++) asm volatile("" : "+f"(d[i])::"memory");
}

__device__ __forceinline__ uint32_t lds32(uint32_t a) {
  uint32_t v;
  asm volatile("ld.volatile.shared.u32 %0, [%1];" : "=r"(v) : "r"(a) : "memory");
  return v;
}
__device__ __forceinline__ uint4 ldg128(const void* a) {
  uint4 v;
  asm volatile("ld.global.nc.v4.u32 {%0, %1, %2, %3}, [%4];" : "=r"(v.x), "=r"(v.y), "=r"(v.z), "=r"(v.w) : "l"(a) : "memory");
  return v;
}
__device__ __forceinline__ uint2 ldg64(const void* a) {
  uint2 v;
  asm volatile("ld.global.nc.v2.u32 {%0, %1}, [%2];" : "=r"(v.x), "=r"(v.y) : "l"(a) : "memory");
  return v;
}
__device__ __forceinline__ void ldsm4(uint32_t* r, uint32_t a) {
  asm volatile("ldmatrix.sync.aligned.m8n8.x4.shared.b16 {%0, %1, %2, %3}, [%4];"
               : "=r"(r[0]), "=r"(r[1]), "=r"(r[2]), "=r"(r[3]) : "r"(a) : "memory");
}
__device__ __forceinline__ void ldsm4t(uint32_t* r, uint32_t a) {
  asm volatile("ldmatrix.sync.aligned.m8n8.x4.trans.shared.b16 {%0, %1, %2, %3}, [%4];"
               : "=r"(r[0]), "=r"(r[1]), "=r"(r[2]), "=r"(r[3]) : "r"(a) : "memory");
}
__device__ __forceinline__ uint4 lds128(uint32_t a) {
  uint4 v;
  asm volatile("ld.shared.v4.u32 {%0, %1, %2, %3}, [%4];" : "=r"(v.x), "=r"(v.y), "=r"(v.z), "=r"(v.w) : "r"(a) : "memory");
  return v;
}
__device__ __forceinline__ void sts128(uint32_t a, uint32_t x, uint32_t y, uint32_t z, uint32_t w) {
  asm volatile("st.shared.v4.u32 [%0], {%1, %2, %3, %4};" ::"r"(a), "r"(x), "r"(y), "r"(z), "r"(w) : "memory");
}
__device__ __forceinline__ void stsm4(uint32_t a, const uint32_t* r) {
  asm volatile("stmatrix.sync.aligned.m8n8.x4.shared.b16 [%0], {%1, %2, %3, %4};" ::"r"(a), "r"(r[0]), "r"(r[1]), "r"(r[2]), "r"(r[3]) : "memory");
}
__device__ __forceinline__ void stsm4t(uint32_t a, const uint32_t* r) {
  asm volatile("stmatrix.sync.aligned.m8n8.x4.trans.shared.b16 [%0], {%1, %2, %3, %4};" ::"r"(a), "r"(r[0]), "r"(r[1]), "r"(r[2]), "r"(r[3]) : "memory");
}
__device__ __forceinline__ uint32_t pack2(float lo, float hi) {
  uint32_t r;
  asm("cvt.rn.bf16x2.f32 %0, %1, %2;" : "=r"(r) : "f"(hi), "f"(lo));
  return r;
}
__device__ __forceinline__ uint32_t movm(uint32_t a) {
  uint32_t d;
  asm volatile("movmatrix.sync.aligned.m8n8.trans.b16 %0, %1;" : "=r"(d) : "r"(a));
  return d;
}
__device__ __forceinline__ uint32_t bmul(uint32_t a, uint32_t b) {
  uint32_t d;
  asm("mul.rn.bf16x2 %0, %1, %2;" : "=r"(d) : "r"(a), "r"(b));
  return d;
}
__device__ __forceinline__ uint32_t badd(uint32_t a, uint32_t b) {
  uint32_t d;
  asm("add.rn.bf16x2 %0, %1, %2;" : "=r"(d) : "r"(a), "r"(b));
  return d;
}
__device__ __forceinline__ float bf_lo(uint32_t x) { return __uint_as_float(x << 16); }
__device__ __forceinline__ float bf_hi(uint32_t x) { return __uint_as_float(x & 0xFFFF0000u); }
__device__ __forceinline__ float ex2(float x) {
  float y;
  asm("ex2.approx.ftz.f32 %0, %1;" : "=f"(y) : "f"(x));
  return y;
}
__device__ __forceinline__ float rcp(float x) {
  float y;
  asm("rcp.approx.ftz.f32 %0, %1;" : "=f"(y) : "f"(x));
  return y;
}
__device__ __forceinline__ void mma16816(float* d, uint32_t a0, uint32_t a1, uint32_t a2, uint32_t a3, uint32_t b0, uint32_t b1) {
  asm volatile("mma.sync.aligned.m16n8k16.row.col.f32.bf16.bf16.f32 {%0, %1, %2, %3}, {%4, %5, %6, %7}, {%8, %9}, {%0, %1, %2, %3};"
               : "+f"(d[0]), "+f"(d[1]), "+f"(d[2]), "+f"(d[3])
               : "r"(a0), "r"(a1), "r"(a2), "r"(a3), "r"(b0), "r"(b1));
}
__device__ __forceinline__ void mma1688(float* d, uint32_t a0, uint32_t a1, uint32_t b0) {
  asm volatile("mma.sync.aligned.m16n8k8.row.col.f32.bf16.bf16.f32 {%0, %1, %2, %3}, {%4, %5}, {%6}, {%0, %1, %2, %3};"
               : "+f"(d[0]), "+f"(d[1]), "+f"(d[2]), "+f"(d[3])
               : "r"(a0), "r"(a1), "r"(b0));
}

template <int N> struct WgRS;
template <int N> struct WgSST;
template <> struct WgRS<32> {
  template <uint32_t HB>
  static __device__ __forceinline__ void mma(float* d, const uint32_t* a, uint32_t db) {
    asm volatile("{\n.reg .pred p;\n.reg .b64 db;\nsetp.ne.b32 p, %22, 0;\n"
      "mov.b64 db, {%20, %21};\n"
      "wgmma.mma_async.sync.aligned.m64n32k16.f32.bf16.bf16 {"
      "%0, %1, %2, %3, %4, %5, %6, %7, %8, %9, %10, %11, %12, %13, %14, %15"
      "}, {%16, %17, %18, %19}, db, p, 1, 1, 1;\n}\n"
      : "+f"(d[0]), "+f"(d[1]), "+f"(d[2]), "+f"(d[3]), "+f"(d[4]), "+f"(d[5]), "+f"(d[6]), "+f"(d[7]),
        "+f"(d[8]), "+f"(d[9]), "+f"(d[10]), "+f"(d[11]), "+f"(d[12]), "+f"(d[13]), "+f"(d[14]), "+f"(d[15])
      : "r"(a[0]), "r"(a[1]), "r"(a[2]), "r"(a[3]), "r"(db), "n"(HB), "n"(1));
  }
  template <uint32_t HB>
  static __device__ __forceinline__ void set(float* d, const uint32_t* a, uint32_t db) {
    asm volatile("{\n.reg .pred p;\n.reg .b64 db;\nsetp.ne.b32 p, %22, 0;\n"
      "mov.b64 db, {%20, %21};\n"
      "wgmma.mma_async.sync.aligned.m64n32k16.f32.bf16.bf16 {"
      "%0, %1, %2, %3, %4, %5, %6, %7, %8, %9, %10, %11, %12, %13, %14, %15"
      "}, {%16, %17, %18, %19}, db, p, 1, 1, 1;\n}\n"
      : "=f"(d[0]), "=f"(d[1]), "=f"(d[2]), "=f"(d[3]), "=f"(d[4]), "=f"(d[5]), "=f"(d[6]), "=f"(d[7]),
        "=f"(d[8]), "=f"(d[9]), "=f"(d[10]), "=f"(d[11]), "=f"(d[12]), "=f"(d[13]), "=f"(d[14]), "=f"(d[15])
      : "r"(a[0]), "r"(a[1]), "r"(a[2]), "r"(a[3]), "r"(db), "n"(HB), "n"(0));
  }
};
template <> struct WgRS<64> {
  template <uint32_t HB>
  static __device__ __forceinline__ void mma(float* d, const uint32_t* a, uint32_t db) {
    asm volatile("{\n.reg .pred p;\n.reg .b64 db;\nsetp.ne.b32 p, %38, 0;\n"
      "mov.b64 db, {%36, %37};\n"
      "wgmma.mma_async.sync.aligned.m64n64k16.f32.bf16.bf16 {"
      "%0, %1, %2, %3, %4, %5, %6, %7, %8, %9, %10, %11, %12, %13, %14, %15, "
      "%16, %17, %18, %19, %20, %21, %22, %23, %24, %25, %26, %27, %28, %29, %30, %31"
      "}, {%32, %33, %34, %35}, db, p, 1, 1, 1;\n}\n"
      : "+f"(d[0]), "+f"(d[1]), "+f"(d[2]), "+f"(d[3]), "+f"(d[4]), "+f"(d[5]), "+f"(d[6]), "+f"(d[7]),
        "+f"(d[8]), "+f"(d[9]), "+f"(d[10]), "+f"(d[11]), "+f"(d[12]), "+f"(d[13]), "+f"(d[14]), "+f"(d[15]),
        "+f"(d[16]), "+f"(d[17]), "+f"(d[18]), "+f"(d[19]), "+f"(d[20]), "+f"(d[21]), "+f"(d[22]), "+f"(d[23]),
        "+f"(d[24]), "+f"(d[25]), "+f"(d[26]), "+f"(d[27]), "+f"(d[28]), "+f"(d[29]), "+f"(d[30]), "+f"(d[31])
      : "r"(a[0]), "r"(a[1]), "r"(a[2]), "r"(a[3]), "r"(db), "n"(HB), "n"(1));
  }
  template <uint32_t HB>
  static __device__ __forceinline__ void set(float* d, const uint32_t* a, uint32_t db) {
    asm volatile("{\n.reg .pred p;\n.reg .b64 db;\nsetp.ne.b32 p, %38, 0;\n"
      "mov.b64 db, {%36, %37};\n"
      "wgmma.mma_async.sync.aligned.m64n64k16.f32.bf16.bf16 {"
      "%0, %1, %2, %3, %4, %5, %6, %7, %8, %9, %10, %11, %12, %13, %14, %15, "
      "%16, %17, %18, %19, %20, %21, %22, %23, %24, %25, %26, %27, %28, %29, %30, %31"
      "}, {%32, %33, %34, %35}, db, p, 1, 1, 1;\n}\n"
      : "=f"(d[0]), "=f"(d[1]), "=f"(d[2]), "=f"(d[3]), "=f"(d[4]), "=f"(d[5]), "=f"(d[6]), "=f"(d[7]),
        "=f"(d[8]), "=f"(d[9]), "=f"(d[10]), "=f"(d[11]), "=f"(d[12]), "=f"(d[13]), "=f"(d[14]), "=f"(d[15]),
        "=f"(d[16]), "=f"(d[17]), "=f"(d[18]), "=f"(d[19]), "=f"(d[20]), "=f"(d[21]), "=f"(d[22]), "=f"(d[23]),
        "=f"(d[24]), "=f"(d[25]), "=f"(d[26]), "=f"(d[27]), "=f"(d[28]), "=f"(d[29]), "=f"(d[30]), "=f"(d[31])
      : "r"(a[0]), "r"(a[1]), "r"(a[2]), "r"(a[3]), "r"(db), "n"(HB), "n"(0));
  }
};
template <> struct WgSST<48> {
  template <uint32_t HA, uint32_t HB>
  static __device__ __forceinline__ void mma(float* d, uint32_t da, uint32_t db, int sc) {
    asm volatile("{\n.reg .pred p;\n.reg .b64 da, db;\nsetp.ne.b32 p, %28, 0;\n"
      "mov.b64 da, {%24, %25};\nmov.b64 db, {%26, %27};\n"
      "wgmma.mma_async.sync.aligned.m64n48k16.f32.bf16.bf16 {"
      "%0, %1, %2, %3, %4, %5, %6, %7, %8, %9, %10, %11, %12, %13, %14, %15, "
      "%16, %17, %18, %19, %20, %21, %22, %23"
      "}, da, db, p, 1, 1, 0, 1;\n}\n"
      : "+f"(d[0]), "+f"(d[1]), "+f"(d[2]), "+f"(d[3]), "+f"(d[4]), "+f"(d[5]), "+f"(d[6]), "+f"(d[7]),
        "+f"(d[8]), "+f"(d[9]), "+f"(d[10]), "+f"(d[11]), "+f"(d[12]), "+f"(d[13]), "+f"(d[14]), "+f"(d[15]),
        "+f"(d[16]), "+f"(d[17]), "+f"(d[18]), "+f"(d[19]), "+f"(d[20]), "+f"(d[21]), "+f"(d[22]), "+f"(d[23])
      : "r"(da), "n"(HA), "r"(db), "n"(HB), "r"(sc));
  }
};
template <> struct WgSST<80> {
  template <uint32_t HA, uint32_t HB>
  static __device__ __forceinline__ void mma(float* d, uint32_t da, uint32_t db, int sc) {
    asm volatile("{\n.reg .pred p;\n.reg .b64 da, db;\nsetp.ne.b32 p, %44, 0;\n"
      "mov.b64 da, {%40, %41};\nmov.b64 db, {%42, %43};\n"
      "wgmma.mma_async.sync.aligned.m64n80k16.f32.bf16.bf16 {"
      "%0, %1, %2, %3, %4, %5, %6, %7, %8, %9, %10, %11, %12, %13, %14, %15, "
      "%16, %17, %18, %19, %20, %21, %22, %23, %24, %25, %26, %27, %28, %29, %30, %31, "
      "%32, %33, %34, %35, %36, %37, %38, %39"
      "}, da, db, p, 1, 1, 0, 1;\n}\n"
      : "+f"(d[0]), "+f"(d[1]), "+f"(d[2]), "+f"(d[3]), "+f"(d[4]), "+f"(d[5]), "+f"(d[6]), "+f"(d[7]),
        "+f"(d[8]), "+f"(d[9]), "+f"(d[10]), "+f"(d[11]), "+f"(d[12]), "+f"(d[13]), "+f"(d[14]), "+f"(d[15]),
        "+f"(d[16]), "+f"(d[17]), "+f"(d[18]), "+f"(d[19]), "+f"(d[20]), "+f"(d[21]), "+f"(d[22]), "+f"(d[23]),
        "+f"(d[24]), "+f"(d[25]), "+f"(d[26]), "+f"(d[27]), "+f"(d[28]), "+f"(d[29]), "+f"(d[30]), "+f"(d[31]),
        "+f"(d[32]), "+f"(d[33]), "+f"(d[34]), "+f"(d[35]), "+f"(d[36]), "+f"(d[37]), "+f"(d[38]), "+f"(d[39])
      : "r"(da), "n"(HA), "r"(db), "n"(HB), "r"(sc));
  }
};
template <> struct WgSST<192> {
  template <uint32_t HA, uint32_t HB>
  static __device__ __forceinline__ void mma(float* d, uint32_t da, uint32_t db, int sc) {
    asm volatile("{\n.reg .pred p;\n.reg .b64 da, db;\nsetp.ne.b32 p, %100, 0;\n"
      "mov.b64 da, {%96, %97};\nmov.b64 db, {%98, %99};\n"
      "wgmma.mma_async.sync.aligned.m64n192k16.f32.bf16.bf16 {"
      "%0, %1, %2, %3, %4, %5, %6, %7, %8, %9, %10, %11, %12, %13, %14, %15, "
      "%16, %17, %18, %19, %20, %21, %22, %23, %24, %25, %26, %27, %28, %29, %30, %31, "
      "%32, %33, %34, %35, %36, %37, %38, %39, %40, %41, %42, %43, %44, %45, %46, %47, "
      "%48, %49, %50, %51, %52, %53, %54, %55, %56, %57, %58, %59, %60, %61, %62, %63, "
      "%64, %65, %66, %67, %68, %69, %70, %71, %72, %73, %74, %75, %76, %77, %78, %79, "
      "%80, %81, %82, %83, %84, %85, %86, %87, %88, %89, %90, %91, %92, %93, %94, %95"
      "}, da, db, p, 1, 1, 0, 1;\n}\n"
      : "+f"(d[0]), "+f"(d[1]), "+f"(d[2]), "+f"(d[3]), "+f"(d[4]), "+f"(d[5]), "+f"(d[6]), "+f"(d[7]),
        "+f"(d[8]), "+f"(d[9]), "+f"(d[10]), "+f"(d[11]), "+f"(d[12]), "+f"(d[13]), "+f"(d[14]), "+f"(d[15]),
        "+f"(d[16]), "+f"(d[17]), "+f"(d[18]), "+f"(d[19]), "+f"(d[20]), "+f"(d[21]), "+f"(d[22]), "+f"(d[23]),
        "+f"(d[24]), "+f"(d[25]), "+f"(d[26]), "+f"(d[27]), "+f"(d[28]), "+f"(d[29]), "+f"(d[30]), "+f"(d[31]),
        "+f"(d[32]), "+f"(d[33]), "+f"(d[34]), "+f"(d[35]), "+f"(d[36]), "+f"(d[37]), "+f"(d[38]), "+f"(d[39]),
        "+f"(d[40]), "+f"(d[41]), "+f"(d[42]), "+f"(d[43]), "+f"(d[44]), "+f"(d[45]), "+f"(d[46]), "+f"(d[47]),
        "+f"(d[48]), "+f"(d[49]), "+f"(d[50]), "+f"(d[51]), "+f"(d[52]), "+f"(d[53]), "+f"(d[54]), "+f"(d[55]),
        "+f"(d[56]), "+f"(d[57]), "+f"(d[58]), "+f"(d[59]), "+f"(d[60]), "+f"(d[61]), "+f"(d[62]), "+f"(d[63]),
        "+f"(d[64]), "+f"(d[65]), "+f"(d[66]), "+f"(d[67]), "+f"(d[68]), "+f"(d[69]), "+f"(d[70]), "+f"(d[71]),
        "+f"(d[72]), "+f"(d[73]), "+f"(d[74]), "+f"(d[75]), "+f"(d[76]), "+f"(d[77]), "+f"(d[78]), "+f"(d[79]),
        "+f"(d[80]), "+f"(d[81]), "+f"(d[82]), "+f"(d[83]), "+f"(d[84]), "+f"(d[85]), "+f"(d[86]), "+f"(d[87]),
        "+f"(d[88]), "+f"(d[89]), "+f"(d[90]), "+f"(d[91]), "+f"(d[92]), "+f"(d[93]), "+f"(d[94]), "+f"(d[95])
      : "r"(da), "n"(HA), "r"(db), "n"(HB), "r"(sc));
  }
};

struct FftConst {
  uint32_t f[2][4], fi[4][4];
  float ta[4], tb[4];
};
__device__ __forceinline__ void cis(int m, float scale, float& c, float& s) {
  const float a = (float)m * (-6.283185307179586f * scale);
  c = __cosf(a);
  s = __sinf(a);
}
__device__ __forceinline__ void fft_tables(uint32_t (&v)[12], int tw) {
  const int row = tw >> 2, ch = tw & 3;
#pragma unroll
  for (int i = 0; i < 4; i++) {
    float c[2], s[2], x[2];
#pragma unroll
    for (int e = 0; e < 2; e++) {
      cis((((32 * (8 * ch + 2 * i + e) + 15) * (4 * row - 63) + 2048) & 4095) - 2048, 1.f / 4096, c[e], s[e]);
      float gc, gs;
      cis((((row & 15) * (8 * (ch & 1) + 2 * i + e) + 8) & 15) - 8, 1.f / 16, gc, gs);
      x[e] = (row >> 4) == (ch >> 1) ? gc : (ch >> 1) ? gs : -gs;
    }
    v[i] = pack2(c[0] * 0.125f, c[1] * 0.125f);
    v[4 + i] = pack2(s[0] * 0.125f, s[1] * 0.125f);
    v[8 + i] = pack2(x[0], x[1]);
  }
#pragma unroll
  for (int i = 0; i < 12; i++) asm volatile("" : "+r"(v[i]));
}
__device__ __forceinline__ void fft_tables_store(const uint32_t (&v)[12], uint32_t sb, int tw) {
  const int row = tw >> 2;
  const uint32_t x = ((tw ^ (row >> 1)) & 3) << 4, a = sb + OFF_FT + (16 * (row >> 3) + (row & 7)) * 64 + x;
  sts128(a, v[0], v[1], v[2], v[3]);
  sts128(a + 512, v[4], v[5], v[6], v[7]);
  sts128(sb + OFF_GT + row * 64 + x, v[8], v[9], v[10], v[11]);
}
__device__ __forceinline__ void fft_twiddles(float (&v)[4], int tw) {
#pragma unroll
  for (int i = 0; i < 2; i++) {
    float c, s;
    cis((2 * (2 * (tw & 3) + i) - 15) * (4 * (tw >> 2) - 63), 1.f / 4096, c, s);
    v[2 * i] = __fdividef(-s, 1.f + c);
    v[2 * i + 1] = s;
  }
  pin<4>(v);
}
__device__ __forceinline__ void fft_matrices(FftConst& k, uint32_t sb, int w, int lane) {
  const uint32_t x = (lane >> 1) & 3;
  const uint4 t0 = lds128(sb + OFF_TT + 512 * w + 16 * lane), t1 = lds128(sb + OFF_TT + 512 * w + 16 * (lane ^ 3));
  k.ta[0] = __uint_as_float(t0.x); k.tb[0] = __uint_as_float(t0.y); k.ta[1] = __uint_as_float(t0.z); k.tb[1] = __uint_as_float(t0.w);
  k.ta[3] = __uint_as_float(t1.x); k.tb[3] = __uint_as_float(t1.y); k.ta[2] = __uint_as_float(t1.z); k.tb[2] = __uint_as_float(t1.w);
#pragma unroll
  for (int i = 0; i < 2; i++) {
    ldsm4(k.f[i], sb + OFF_FT + (16 * w + (lane & 15)) * 64 + (((2 * i + (lane >> 4)) ^ x) << 4));
    ldsm4t(k.fi[i], sb + OFF_FT + (32 * i + lane) * 64 + ((w ^ x) << 4));
#pragma unroll
    for (int j = 0; j < 4; j++) {
      k.fi[2 + i][j] = (j & 1) ? k.fi[i][j - 1] ^ 0x80008000u : k.fi[i][j + 1];
      asm volatile("" : "+r"(k.fi[2 + i][j]));
    }
  }
}
__device__ __forceinline__ void rot(bool inv, float& x, float& y, float a, float b) {
  x = fmaf(inv ? -a : a, y, x);
  y = fmaf(inv ? -b : b, x, y);
  x = fmaf(inv ? -a : a, y, x);
}
__device__ __forceinline__ void twiddle_fwd(uint32_t (&a)[4][4], float* d, const FftConst& k) {
#pragma unroll
  for (int q = 0; q < 4; q++)
#pragma unroll
    for (int j = 0; j < 2; j++) {
      float* x = d + 8 * q + 4 * j;
      rot(j, x[0], x[2], k.ta[2 * j], k.tb[2 * j]);
      rot(j, x[1], x[3], k.ta[2 * j + 1], k.tb[2 * j + 1]);
      a[q & 2][2 * j + (q & 1)] = pack2(x[0], x[1]);
      a[(q & 2) + 1][2 * j + (q & 1)] = pack2(x[2], x[3]);
    }
}
__device__ __forceinline__ void g_step(float* d, const uint32_t (&a)[4][4], uint32_t dre, uint32_t dim) {
  WgRS<32>::set<HI_SW64>(d, a[0], dre);
  WgRS<32>::set<HI_SW64>(d + 16, a[2], dre);
  WgRS<32>::mma<HI_SW64>(d, a[1], dim);
  WgRS<32>::mma<HI_SW64>(d + 16, a[3], dim);
  wg_commit();
}

__device__ __forceinline__ void conv_channel(const FftConst& k, uint32_t sb, int c, int wg, int w, int lane) {
  const uint32_t cb = sb + off_ch(c), bars = sb + OFF_BAR;
  const uint32_t du = desc_lo(cb, 1024), dg = desc_lo(sb + OFF_GT, 16), dz = desc_lo(cb + U_BYTES, 16);
  float U[32], H[32];
  uint32_t a[4][4], e[4][4];
  const float dv = __uint_as_float(lds32(sb + OFF_D + 4 * c));
  wg_fence();
  WgRS<64>::set<HI_SW32>(H, k.f[0], du + 256);
  WgRS<64>::mma<HI_SW32>(H, k.f[1], du + 256 + 32);
  wg_commit();
  wg_wait<0>();
  pin<32>(H);
  twiddle_fwd(a, H, k);
  if (ATT_GATE && H_EARLY) mbar_wait(bars + 8 * B_ATTN, 0);
  mbar_wait(bars + 8 * (B_U + (c < 3 ? c : 3)), 0);
  TSM(w == 0 && c < 3, 7 + wg);
  wg_fence();
  WgRS<64>::set<HI_SW32>(U, k.f[0], du);
  WgRS<64>::mma<HI_SW32>(U, k.f[1], du + 32);
  wg_commit();
  g_step(H, a, dg, dg + 64);
  wg_wait<1>();
  pin<32>(U);
  twiddle_fwd(e, U, k);
  wg_fence();
  g_step(U, e, dg, dg + 64);
  wg_wait<0>();
  pin<32>(U);
  pin<32>(H);
#pragma unroll
  for (int j = 0; j < 2; j++) {
    float pr[4][2], pi[4][2];
#pragma unroll
    for (int x = 0; x < 2; x++) {
      H[4 * j + x] += dv;
#pragma unroll
      for (int m = 0; m < 4; m++) {
#pragma unroll
        for (int q = 0; q <= m; q++) {
          const int ih = 16 * (q >> 1) + 2 * (q & 1) + 4 * j + x, iu = 16 * ((m - q) >> 1) + 2 * ((m - q) & 1) + 4 * j + x;
          pr[m][x] = q ? fmaf(H[ih], U[iu], pr[m][x]) : H[ih] * U[iu];
          pi[m][x] = q ? fmaf(H[ih], U[iu + 8], pi[m][x]) : H[ih] * U[iu + 8];
          pr[m][x] = fmaf(-H[ih + 8], U[iu + 8], pr[m][x]);
          pi[m][x] = fmaf(H[ih + 8], U[iu], pi[m][x]);
        }
      }
    }
#pragma unroll
    for (int m = 0; m < 4; m++) {
      a[m & 2][2 * j + (m & 1)] = pack2(pr[m][0], pr[m][1]);
      a[(m & 2) + 1][2 * j + (m & 1)] = pack2(pi[m][0], pi[m][1]);
    }
  }
  wg_fence();
  g_step(U, a, dg + 64, dg);
  const uint32_t za = cb + U_BYTES + (8 * w + (lane & 7)) * 128 + (((lane >> 3) ^ (lane & 7)) << 4);
  const uint32_t ya = cb + (lane >> 4) * 1024 + (8 * w + (lane & 7)) * 32 + ((((lane >> 3) ^ (lane >> 2)) & 1) << 4);
  wg_sync(1 + wg);
  wg_wait<0>();
  pin<32>(U);
  TSIF(w == 0, 80 + c);
#pragma unroll
  for (int p = 0; p < 2; p++) {
#pragma unroll
    for (int i = 0; i < 4; i++) {
      const int j = i & 1;
      float* x = U + 16 * p + 4 * j + (i & 2);
      rot(!j, x[8], x[0], k.ta[2 * j], k.tb[2 * j]);
      rot(!j, x[9], x[1], k.ta[2 * j + 1], k.tb[2 * j + 1]);
      e[p][i] = pack2(x[8], x[9]);
      e[2 + p][i] = pack2(x[0], x[1]);
    }
    stsm4(za ^ (64 * p), e[p]);
    stsm4((za ^ (64 * p)) + 4096, e[2 + p]);
  }
  fence_async_smem();
  wg_sync(1 + wg);
  wg_fence();
  WgRS<64>::set<HI_SW128>(H, k.fi[0], dz);
#pragma unroll
  for (int ks = 1; ks < 4; ks++) WgRS<64>::mma<HI_SW128>(H, k.fi[ks], dz + 128 * ks);
  wg_commit();
  wg_wait<0>();
  pin<32>(H);
  TSIF(w == 0, 88 + c);
#pragma unroll
  for (int j = 0; j < 8; j++)
    a[j >> 2][j & 3] = j < 2 ? pack2(H[4 * j], H[4 * j + 1]) : pack2(H[4 * j] + H[4 * j - 6], H[4 * j + 1] + H[4 * j - 5]);
  stsm4(ya, a[0]);
  stsm4(ya + 2048, a[1]);
  fence_async_smem();
  __syncwarp();
}

__device__ __forceinline__ void prep_slab(uint4* res, const uint2* sw, uint32_t sb, int slab, int w, int lane) {
  const int t = lane & 3, tp = (lane & 7) >> 1, pos = 8 * tp + 2 * (((lane >> 3) + tp) & 3) + (lane & 1);
  const uint32_t base = sb + OFF_KVS + slab * KVS_BYTES + pos * 128;
  uint32_t kk[2][4][4], vv[2][4];
  mbar_wait(sb + OFF_BAR + 8 * (B_KV + slab), 0);
#pragma unroll
  for (int h = 0; h < 2; h++) {
#pragma unroll
    for (int j = 0; j < 4; j++) {
      const uint32_t a = base + 128 * j;
      ldsm4t(kk[h][j], a + (((w + 4 * h) ^ ((a >> 7) & 7)) << 4));
    }
    const uint32_t a = base + KVS_V;
    ldsm4t(vv[h], a + (((w + 4 * h) ^ ((a >> 7) & 7)) << 4));
  }
#pragma unroll
  for (int h = 0; h < 2; h++) {
    uint32_t (&k)[4][4] = kk[h];
    uint32_t (&v)[4] = vv[h];
    const uint32_t w0 = __byte_perm(sw[h].x, 0, 0x1010), w1 = __byte_perm(sw[h].x, 0, 0x3232);
    const uint32_t w2 = __byte_perm(sw[h].y, 0, 0x1010), w3 = __byte_perm(sw[h].y, 0, 0x3232);
#pragma unroll
    for (int m = 0; m < 4; m++)
      v[m] = bmul(badd(badd(badd(bmul(k[0][m], w3), bmul(k[1][m], w2)), bmul(k[2][m], w1)), bmul(k[3][m], w0)), v[m]);
    uint32_t a[4];
#pragma unroll
    for (int m = 0; m < 4; m++) a[m] = (t & 1) ? v[(m + 3) & 3] : v[m];
    res[h] = (t & 2) ? make_uint4(a[2], a[3], a[0], a[1]) : make_uint4(a[0], a[1], a[2], a[3]);
  }
}

__device__ __forceinline__ void gate_step(float (&z)[4], uint32_t (&gw)[10], uint32_t sb, uint32_t xa, int kb, int lane, uint32_t zero) {
  mbar_wait(sb + OFF_BAR + 8 * (B_FULL1 + (kb & 3)), (kb >> 2) & 1);
  uint32_t x[4];
#pragma unroll
  for (int i = 0; i < 4; i++) x[i] = lds32((xa ^ (144 * (i >> 1))) + (i & 1) * 8192 + (kb & 3) * STAGE_BYTES);
#pragma unroll
  for (int i = 0; i < 4; i++) {
    const uint32_t m = bmul(x[i], gw[0]);
    z[i] += bf_lo(m) + bf_hi(m);
  }
#pragma unroll
  for (int i = 0; i < 9; i++) gw[i] = gw[i + 1];
  __syncwarp();
  if (lane == 0) mbar_arrive(sb + OFF_BAR + 8 * (kb == 3 ? B_E3 : kb == 9 ? B_P1 : B_EMPTY1 + (kb & 3)) + ((x[0] ^ x[1] ^ x[2] ^ x[3]) & zero));
}

__device__ __forceinline__ uint32_t bmax(uint32_t a, uint32_t b) {
  uint32_t d;
  asm("max.bf16x2 %0, %1, %2;" : "=r"(d) : "r"(a), "r"(b));
  return d;
}
__device__ __forceinline__ void softmax_two(const float (&l)[2][2], uint32_t& p0, uint32_t& p1) {
  constexpr float kScale = 0.22360679774997896f, kLog2e = 1.4426950408889634f;
  const uint32_t r0 = pack2(l[0][0], l[1][0]), r1 = pack2(l[0][1], l[1][1]);
  const uint32_t x0 = pack2(bf_lo(r0) * kScale, bf_hi(r0) * kScale), x1 = pack2(bf_lo(r1) * kScale, bf_hi(r1) * kScale);
  uint32_t m = bmax(x0, x1);
  m = bmax(m, __shfl_xor_sync(0xffffffffu, m, 1));
  m = bmax(m, __shfl_xor_sync(0xffffffffu, m, 2));
  const float m0 = bf_lo(m) * kLog2e, m1 = bf_hi(m) * kLog2e;
  p0 = pack2(ex2(bf_lo(x0) * kLog2e - m0), ex2(bf_lo(x1) * kLog2e - m0));
  p1 = pack2(ex2(bf_hi(x0) * kLog2e - m1), ex2(bf_hi(x1) * kLog2e - m1));
}

__device__ __forceinline__ void halo_read(uint32_t (&kpv)[10], uint32_t (&vpv)[10], uint32_t (&tg)[7], const uint4* hp) {
#pragma unroll
  for (int j = 0; j < 7; j++) {
    uint32_t x0, x1, x2;
    asm volatile("ld.relaxed.gpu.global.v4.u32 {%0, %1, %2, %3}, [%4];"
                 : "=r"(x0), "=r"(x1), "=r"(x2), "=r"(tg[j]) : "l"(hp + 32 * j) : "memory");
    if (j < 4) kpv[3 * j] = x0; else vpv[3 * j - 10] = x0;
    if (j < 3) kpv[3 * j + 1] = x1; else vpv[3 * j - 9] = x1;
    if (j < 3) kpv[3 * j + 2] = x2; else if (j < 6) vpv[3 * j - 8] = x2;
  }
}

template <int ROT>
__device__ __forceinline__ void pack_qkv(const float* acc, uint32_t (&qlo)[10], uint32_t (&qhi)[10], uint32_t (&klo)[10],
                                         uint32_t (&khi)[10], uint32_t (&vlo)[10], uint32_t (&vhi)[10]) {
#pragma unroll
  for (int j = 0; j < 10; j++) {
    const int x = (j + ROT) % 10, tq = x < 8 ? x : 16 + x, tk = x < 8 ? 8 + x : 18 + x, tv = x < 8 ? 16 + x : 20 + x;
    khi[j] = pack2(acc[4 * tk + 2], acc[4 * tk + 3]);
    vhi[j] = movm(pack2(acc[4 * tv + 2], acc[4 * tv + 3]));
    qlo[j] = pack2(acc[4 * tq], acc[4 * tq + 1]);
    qhi[j] = pack2(acc[4 * tq + 2], acc[4 * tq + 3]);
    klo[j] = pack2(acc[4 * tk], acc[4 * tk + 1]);
    vlo[j] = pack2(acc[4 * tv], acc[4 * tv + 1]);
    asm volatile("" : "+r"(khi[j]), "+r"(qlo[j]), "+r"(qhi[j]), "+r"(klo[j]), "+r"(vlo[j]));
  }
}

template <int ROT> __device__ __forceinline__ void halo_send(const float* acc, uint4* ho, uint32_t tag) {
#pragma unroll
  for (int j = 0; j < 7; j++) {
    uint32_t x[3];
#pragma unroll
    for (int e = 0; e < 3; e++) {
      const int i = 3 * j + e, y = (i % 10 + ROT) % 10, tk = y < 8 ? 8 + y : 18 + y, tv = y < 8 ? 16 + y : 20 + y;
      x[e] = i < 10 ? pack2(acc[4 * tk + 2], acc[4 * tk + 3]) : i < 20 ? movm(pack2(acc[4 * tv + 2], acc[4 * tv + 3])) : 0u;
    }
    asm volatile("st.relaxed.gpu.global.v4.u32 [%0], {%1, %2, %3, %4};" ::"l"(ho + 32 * j), "r"(x[0]), "r"(x[1]), "r"(x[2]), "r"(tag) : "memory");
  }
}

__device__ __forceinline__ void attention(float* acc, uint32_t sb, int b, int par, int w, int lane, uint32_t tag) {
  const int g = lane >> 2, t = lane & 3;
  uint32_t klo[10], khi[10], vlo[10], vhi[10], qlo[10], qhi[10], kpv[10], vpv[10];
  if (HALO_FIRST && w == 3 && b < NCTA - 8) {
    uint4* ho = g_halo + (b * 2 + par) * 224 + lane;
    if (tail_first(b & 7)) halo_send<8>(acc, ho, tag);
    else halo_send<0>(acc, ho, tag);
    TSIF(par == 0, 76);
    pin<120>(acc);
  }
  if (tail_first(b & 7)) pack_qkv<8>(acc, qlo, qhi, klo, khi, vlo, vhi);
  else pack_qkv<0>(acc, qlo, qhi, klo, khi, vlo, vhi);
  const uint32_t xa = sb + OFF_KVX + (par * 3) * 2560 + lane * 16;
  if (w < 3) {
    sts128(xa + w * 2560, khi[0], khi[1], khi[2], khi[3]);
    sts128(xa + w * 2560 + 512, khi[4], khi[5], khi[6], khi[7]);
    sts128(xa + w * 2560 + 1024, khi[8], khi[9], vhi[0], vhi[1]);
    sts128(xa + w * 2560 + 1536, vhi[2], vhi[3], vhi[4], vhi[5]);
    sts128(xa + w * 2560 + 2048, vhi[6], vhi[7], vhi[8], vhi[9]);
  } else if (!HALO_FIRST && b < NCTA - 8) {
    uint4* ho = g_halo + (b * 2 + par) * 224 + lane;
#pragma unroll
    for (int j = 0; j < 7; j++) {
      const uint32_t x0 = j < 4 ? khi[3 * j] : vhi[3 * j - 10], x1 = j < 3 ? khi[3 * j + 1] : vhi[3 * j - 9];
      const uint32_t x2 = j < 3 ? khi[3 * j + 2] : j < 6 ? vhi[3 * j - 8] : 0u;
      asm volatile("st.relaxed.gpu.global.v4.u32 [%0], {%1, %2, %3, %4};" ::"l"(ho + 32 * j), "r"(x0), "r"(x1), "r"(x2), "r"(tag) : "memory");
    }
  }
  TSIF(par == 0 && w == 1, 64);
  TSIF(par == 0 && w == 3 && !HALO_FIRST, 76);
#pragma unroll
  for (int j = 0; j < 10; j++) vlo[j] = movm(vlo[j]);
  const bool far0 = 2 * t > g, far1 = 2 * t + 1 > g;
  const uint32_t mfar = (far0 ? 0x0000FFFFu : 0u) | (far1 ? 0xFFFF0000u : 0u);
  float slo[4][2], shi[4][2], lg[2][2];
  uint32_t phi[4], plo[4], qml[4], qmh[4];
#pragma unroll
  for (int h = 0; h < 4; h++) {
    const int f = h == 0 ? 0 : h == 1 ? 3 : h == 2 ? 5 : 8, hf = h < 2 ? 2 : 7;
    const bool mine = (h & 1) ? t >= 2 : t < 2;
    qml[h] = mine ? qlo[hf] : 0u;
    qmh[h] = mine ? qhi[hf] : 0u;
    float a[4] = {0.f, 0.f, 0.f, 0.f}, c[4] = {0.f, 0.f, 0.f, 0.f};
    mma16816(a, qlo[f], qhi[f], qlo[f + 1], qhi[f + 1], klo[f], klo[f + 1]);
    mma16816(c, qlo[f], qhi[f], qlo[f + 1], qhi[f + 1], khi[f], khi[f + 1]);
    mma1688(a, qml[h], qmh[h], klo[hf]);
    mma1688(c, qml[h], qmh[h], khi[hf]);
    slo[h][0] = a[0];
    slo[h][1] = a[1];
    shi[h][0] = lg[h & 1][0] = far0 ? a[2] : c[2];
    shi[h][1] = lg[h & 1][1] = far1 ? a[3] : c[3];
    if (!ATT_MERGE && (h & 1)) softmax_two(lg, phi[h - 1], phi[h]);
  }
  TSIF(par == 0 && w == 1, 65);
  wg_sync(1 + par);
  TSIF(par == 0 && w == 1, 66);
  const bool nohist = (w == 0) && (b < 8);
  const uint4* hp = g_halo + ((b - 8) * 2 + par) * 224 + lane;
  uint32_t tg[7];
  if (w > 0) {
    const uint4 v0 = lds128(xa + (w - 1) * 2560), v1 = lds128(xa + (w - 1) * 2560 + 512), v2 = lds128(xa + (w - 1) * 2560 + 1024);
    const uint4 v3 = lds128(xa + (w - 1) * 2560 + 1536), v4 = lds128(xa + (w - 1) * 2560 + 2048);
    kpv[0] = v0.x; kpv[1] = v0.y; kpv[2] = v0.z; kpv[3] = v0.w; kpv[4] = v1.x; kpv[5] = v1.y; kpv[6] = v1.z; kpv[7] = v1.w;
    kpv[8] = v2.x; kpv[9] = v2.y; vpv[0] = v2.z; vpv[1] = v2.w; vpv[2] = v3.x; vpv[3] = v3.y; vpv[4] = v3.z; vpv[5] = v3.w;
    vpv[6] = v4.x; vpv[7] = v4.y; vpv[8] = v4.z; vpv[9] = v4.w;
  } else if (nohist) {
#pragma unroll
    for (int j = 0; j < 10; j++) kpv[j] = vpv[j] = 0u;
  } else {
    TSIF(par == 0, 77);
    halo_read(kpv, vpv, tg, hp);
  }
  if (w == 0 && !nohist) {
    int spins = 0;
    while (true) {
      bool ok = true;
#pragma unroll
      for (int j = 0; j < 7; j++) ok = ok && tg[j] == tag;
      if (__all_sync(0xffffffffu, ok) || ++spins > SPIN_LIMIT) break;
      halo_read(kpv, vpv, tg, hp);
    }
    TSIF(par == 0, 79);
  }
#pragma unroll
  for (int h = 0; h < 4; h++) {
    const int f = h == 0 ? 0 : h == 1 ? 3 : h == 2 ? 5 : 8, hf = h < 2 ? 2 : 7;
    float a[4] = {0.f, 0.f, 0.f, 0.f};
    mma16816(a, qlo[f], qhi[f], qlo[f + 1], qhi[f + 1], kpv[f], kpv[f + 1]);
    mma1688(a, qml[h], qmh[h], kpv[hf]);
    const float ninf = __int_as_float(0xff800000);
    lg[h & 1][0] = far0 ? (nohist ? ninf : a[0]) : slo[h][0];
    lg[h & 1][1] = far1 ? (nohist ? ninf : a[1]) : slo[h][1];
    if (h & 1) {
      softmax_two(lg, plo[h - 1], plo[h]);
      if (ATT_MERGE) {
        const float lh[2][2] = {{shi[h - 1][0], shi[h - 1][1]}, {shi[h][0], shi[h][1]}};
        softmax_two(lh, phi[h - 1], phi[h]);
      }
    }
  }
  TSIF(par == 0 && w <= 1, 67 + w);
  uint32_t ov[20];
#pragma unroll
  for (int hp = 0; hp < 2; hp++) {
    const int hf = hp ? 7 : 2;
    float sh[4] = {0.f, 0.f, 0.f, 0.f}, i0 = 0.f, i1 = 0.f;
#pragma unroll
    for (int e = 0; e < 2; e++) {
      const int h = 2 * hp + e, f = h == 0 ? 0 : h == 1 ? 3 : h == 2 ? 5 : 8;
      const uint32_t a0 = plo[h] & mfar, a2 = plo[h] & ~mfar, a3 = phi[h] & mfar, c1 = phi[h] & ~mfar;
      float sum[4] = {0.f, 0.f, 0.f, 0.f};
      mma1688(sum, plo[h], phi[h], 0x3F803F80u);
      const float r0 = rcp(sum[0]), r1 = rcp(sum[2]);
#pragma unroll
      for (int j = f; j < f + 2; j++) {
        float o[4] = {0.f, 0.f, 0.f, 0.f};
        mma16816(o, a0, 0u, a2, a3, vpv[j], vlo[j]);
        mma1688(o, 0u, c1, vhi[j]);
        ov[2 * j] = pack2(o[0] * r0, o[1] * r0);
        ov[2 * j + 1] = pack2(o[2] * r1, o[3] * r1);
      }
      const bool mine = e ? g >= 4 : g < 4;
      mma16816(sh, a0, 0u, a2, a3, mine ? vpv[hf] : 0u, mine ? vlo[hf] : 0u);
      mma1688(sh, 0u, c1, mine ? vhi[hf] : 0u);
      if (e == 0 || t >= 2) {
        i0 = r0;
        i1 = r1;
      }
    }
    ov[2 * hf] = pack2(sh[0] * i0, sh[1] * i0);
    ov[2 * hf + 1] = pack2(sh[2] * i1, sh[3] * i1);
  }
  TS(32 + 4 * par + w);
  mbar_wait(sb + OFF_BAR + 8 * B_P1, 0);
  const uint32_t oa = sb + OFF_OA + (lane >> 4) * 2048 + (32 * w + 2 * (lane & 15) + par) * 16;
#pragma unroll
  for (int j = 0; j < 5; j++) stsm4(oa + 4096 * j, ov + 4 * j);
  TSIF(par == 0 && w == 0, 120);
  fence_async_smem();
  TSIF(par == 0 && w == 0, 121);
  __syncwarp();
  if (lane == 0) mbar_arrive(sb + OFF_BAR + 8 * B_ATTN);
  TSM(w == 0 || w == 2, 122 + par + (w == 2 ? 3 : 0));
}

struct Maps {
  CUtensorMap x, wm, wt, k, v, y, wo, qm, qt, om, ot, u;
};

__device__ __forceinline__ void load_stage(uint32_t sb, int kb, int b, const Maps& m) {
  const uint32_t st = sb + (kb & 3) * STAGE_BYTES, bar = sb + OFF_BAR + 8 * (B_FULL1 + (kb & 3));
  const int r = b >> 3, hg = b & 7, slab = kb - KV_KB;
  const bool kv = slab >= 0 && slab < 5;
  const uint32_t kbar = sb + OFF_BAR + 8 * (B_KV + slab), dst = sb + OFF_KVS + slab * KVS_BYTES;
  mbar_expect_tx(bar, STAGE_BYTES);
  if (kv) mbar_expect_tx(kbar, KVS_BYTES);
  tma_3d(st, &m.x, 64 * kb, 64 * r, 0, bar);
  if (kv && KV_MIX) tma_3d(dst, &m.k, 0, 32 * (b >> 1) - 3, 2 * slab + (b & 1), kbar);
  tma_3d(st + ST_W, &m.wm, 80 * hg + (tail_first(hg) ? 16 : 0), 64 * kb, 0, bar);
  if (kv && KV_MIX) tma_3d(dst + KVS_V, &m.v, 0, 32 * (b >> 1), 2 * slab + (b & 1), kbar);
  tma_3d(st + ST_WT, &m.wt, 80 * hg + (tail_first(hg) ? 0 : 64), 64 * kb, 0, bar);
  if (kv && !KV_MIX) tma_3d(dst, &m.k, 0, 32 * (b >> 1) - 3, 2 * slab + (b & 1), kbar);
  if (kv && !KV_MIX) tma_3d(dst + KVS_V, &m.v, 0, 32 * (b >> 1), 2 * slab + (b & 1), kbar);
}

__global__ void __launch_bounds__(NTHR, 1) fused_kernel(const __grid_constant__ Maps m, const Params p) {
  extern __shared__ __align__(1024) uint8_t smem[];
  const uint32_t sb = (uint32_t)__cvta_generic_to_shared(smem);
  const uint32_t bars = sb + OFF_BAR;
  const int tid = threadIdx.x, lane = tid & 31;
  int b = blockIdx.x;
  if (BMAP == 1) b = (((b & 63) >> 3) * 2 + (b & 1)) * 8 + (((b < 64 ? 0x6521 : 0x7430) >> (4 * ((b >> 1) & 3))) & 7);
  if (BMAP == 2) b = ((b & 63) >> 2) * 8 + (((b < 64 ? 0x6521 : 0x7430) >> (4 * (b & 3))) & 7);
  if (BMAP == 3) b = (((b & 63) >> 3) * 2 + (b & 1)) * 8 + (((b < 64 ? 0x7430 : 0x6521) >> (4 * ((b >> 1) & 3))) & 7);
  if (BMAP == 4) b = (((b >> 4) * 2 + (b & 1)) * 8) + ((b >> 1) & 7);
  if (BMAP == 5) b = 127 - b;
  const int r = b >> 3, hg = b & 7;

  if (tid == T_ISSUE) {
    TSM(true, 0);
#pragma unroll
    for (int i = 0; i < 4; i++) mbar_init(bars + 8 * (B_FULL1 + i), 1);
#pragma unroll
    for (int i = 0; i < 3; i++) mbar_init(bars + 8 * (B_KV + i), 1);
    fence_async_smem();
#pragma unroll 1
    for (int kb = 0; kb <= PRE2; kb++) load_stage(sb, kb, b, m);
  } else if (tid >= T_PF && tid < T_PF + 12) {
    tm_prefetch(&m.x + (tid - T_PF));
  } else if (tid == T_INIT) {
#pragma unroll
    for (int i = 0; i < 4; i++) mbar_init(bars + 8 * (B_EMPTY1 + i), 12);
#pragma unroll
    for (int i = 0; i < 8; i++) mbar_init(bars + 8 * (B_FULL2 + i), 1);
#pragma unroll
    for (int i = 0; i < 4; i++) mbar_init(bars + 8 * (B_EMPTY2 + i), 8);
#pragma unroll
    for (int i = 0; i < 4; i++) mbar_init(bars + 8 * (B_U + i), 1);
    mbar_init(bars + 8 * B_HA, 4);
    mbar_init(bars + 8 * B_GATE, 4);
    mbar_init(bars + 8 * B_HB, 1);
    mbar_init(bars + 8 * B_KVD, 4);
    mbar_init(bars + 8 * B_QF, 1);
    mbar_init(bars + 8 * B_ATTN, 8);
    mbar_init(bars + 8 * B_P1, 12);
    mbar_init(bars + 8 * B_C34, 1);
#pragma unroll
    for (int i = 0; i < 5; i++) mbar_init(bars + 8 * (B_YST + i), 4);
#pragma unroll
    for (int i = 0; i < 5; i++) mbar_init(bars + 8 * (B_US + i), 4);
    mbar_init(bars + 8 * B_YSIG, 1);
    mbar_init(bars + 8 * B_YFULL, 1);
    mbar_init(bars + 8 * B_EPOCH, 1);
    mbar_init(bars + 8 * B_PREP, 4);
    mbar_init(bars + 8 * B_USIG, 1);
    mbar_init(bars + 8 * B_WST, 1);
#pragma unroll
    for (int i = 3; i < 5; i++) mbar_init(bars + 8 * (B_KV + i), 1);
    mbar_init(bars + 8 * B_E3, 12);
    mbar_init(bars + 8 * B_LAST, 1);
    mbar_init(bars + 8 * B_OSIG, 1);
    mbar_init(bars + 8 * B_WOP, 1);
    fence_async_smem();
  }
  const int warp = __shfl_sync(0xffffffffu, tid >> 5, 0), wg = warp >> 2, w = warp & 3;
  __syncthreads();

  if (wg == 3) {
    asm volatile("setmaxnreg.dec.sync.aligned.u32 56;");
    if (w == 0) {
      if (lane == 0) {
#pragma unroll 1
        for (int kb = 1 + PRE2; kb < 10; kb++) {
          if (kb >= 4) mbar_wait(bars + 8 * (kb == 7 ? B_E3 : B_EMPTY1 + (kb & 3)), (kb >> 3) & 1);
          TSIF(kb >= 4, 44 + kb);
          load_stage(sb, kb, b, m);
          TSIF(kb == 3, 60);
          if (kb == TRIG_KB) mbar_arrive(bars + 8 * B_LAST);
        }
        mbar_wait(bars + 8 * B_WOP, 0);
        mbar_wait(bars + 8 * WL_TRIG, 0);
        mbar_wait(bars + 8 * B_EPOCH, 0);
        flag_wait(g_cnt + C_W + 32 * hg, (lds32(sb + OFF_EPOCH) + 1) * 16);
        TS(30);
#pragma unroll 1
        for (int j = 0; j < 8; j++) {
          if (j >= 6) mbar_wait(bars + 8 * (B_EMPTY2 + j - 6), 0);
          if (j == 4) mbar_wait(bars + 8 * B_ATTN, 0);
          TSIF(j >= 6, 100 + j);
          if (RF_GATE && j == 6) mbar_wait(bars + 8 * B_YSIG, 0);
          mbar_expect_tx(bars + 8 * (B_FULL2 + j), j == 0 ? WO_BYTES : j == 5 ? O_BYTES + WO_BYTES + 512 : O_BYTES + WO_BYTES);
          bulk_load(sb + off_w(j), g_WO + (hg * 8 + step_src(hg, j)) * 800, WO_BYTES, bars + 8 * (B_FULL2 + j));
        }
        mbar_wait(bars + 8 * (B_EMPTY2 + 3), 0);
        mbar_expect_tx(bars + 8 * B_QF, O_BYTES);
        tma_2d(sb + OFF_QS, &m.qm, 80 * hg, 128 * r, bars + 8 * B_QF);
        tma_2d(sb + OFF_QT, &m.qt, 80 * hg + 64, 128 * r, bars + 8 * B_QF);
      }
    } else if (w == 1) {
      unsigned epoch = 0;
      if (lane == 0) {
        epoch = atomicAdd(g_cnt + C_LAUNCH, 1u) / NCTA;
        asm volatile("st.shared.u32 [%0], %1;" ::"r"(sb + OFF_EPOCH), "r"(epoch) : "memory");
        mbar_arrive(bars + 8 * B_EPOCH);
        mbar_wait(bars + 8 * B_KVD, 0);
        mbar_expect_tx(bars + 8 * B_HB, 5 * 4096);
#pragma unroll 1
        for (int c = 0; c < 5; c++) {
          if (c == 3) mbar_wait(bars + 8 * B_S3, 0);
          bulk_load(sb + off_ch(c) + U_BYTES, p.ssm_k + (5 * b + c) * SEQ, 4096, bars + 8 * B_HB);
        }
#pragma unroll
        for (int c = 0; c < 4; c++) mbar_expect_tx(bars + 8 * (B_U + c), c < 3 ? U_BYTES : 2 * U_BYTES);
        const uint4* usrc = g_U + 5 * b * U_PITCH;
        mbar_wait(bars + 8 * B_USIG, 0);
        flag_wait(g_cnt + C_PREP + 32 * (b & 15), (epoch + 1) * NCTA);
        TS(23);
#pragma unroll
        for (int c = 0; c < 5; c++) {
          if (c == 3) mbar_wait(bars + 8 * (B_U + 2), 0);
          bulk_load(sb + off_ch(c), usrc + c * U_PITCH, U_BYTES, bars + 8 * (B_U + (c < 3 ? c : 3)));
          TSIF(c == 0 || c == 4, 116 + (c >> 2));
        }
      }
      epoch = __shfl_sync(0xffffffffu, epoch, 0);
      if (lane < 8) {
        const int src = (b & ~7) | step_src(hg, lane);
        mbar_wait(bars + 8 * B_OSIG, 0);
        TS(20);
        flag_wait(g_cnt + C_O + 32 * src, epoch + 1);
        if (lane >= 1 && lane < 4) bulk_load(sb + off_o(lane), g_O + src * 1280, O_BYTES, bars + 8 * (B_FULL2 + lane));
        __syncwarp(0xff);
        TS(21);
        if (lane == 5) bulk_load(sb + OFF_GATE, g_gate + 128 * r, 512, bars + 8 * (B_FULL2 + 5));
#pragma unroll 1
        for (int j = 4; j < 8; j++) {
          if (lane == j) {
            mbar_wait(bars + 8 * (j < 6 ? B_C34 : B_EMPTY2 + j - 6), 0);
            if (RF_GATE && j == 6) mbar_wait(bars + 8 * B_YSIG, 0);
            bulk_load(sb + off_o(j), g_O + src * 1280, O_BYTES, bars + 8 * (B_FULL2 + j));
          }
          __syncwarp(0xff);
        }
        TS(22);
      }
    } else if (w == 2) {
      mbar_wait(bars + 8 * B_PREP, 0);
      flag_signal(g_cnt + C_PREP, 16, lane);
      TS(25);
      if (lane == 0) mbar_arrive(bars + 8 * B_USIG);
      mbar_wait(bars + 8 * B_GATE, 0);
      if ((NOMB & 1) && lane == 0) asm volatile("fence.release.gpu;" ::: "memory");
      mbar_wait(bars + 8 * B_ATTN, 0);
      if (lane == 0) {
        if (O_DEFER) mbar_wait(bars + 8 * (B_U + 3), 0);
        asm volatile("cp.async.bulk.global.shared::cta.bulk_group [%0], [%1], 20480;\ncp.async.bulk.commit_group;\n"
                     "cp.async.bulk.wait_group 0;\nfence.proxy.async.global;" ::"l"(g_O + b * 1280), "r"(sb + OFF_OA) : "memory");
      }
      TS(74);
      if (!(NOMB & 1)) flag_signal(g_cnt + C_O + 32 * b, 1, lane);
      else if (lane == 0) flag_bump(g_cnt + C_O + 32 * b);
      TS(26);
      if (lane == 0) mbar_arrive(bars + 8 * B_OSIG);

    } else {
      if (lane == 0) {
        uint4* dst = g_WO + (hg * 8 + (r >> 1)) * 800 + (r & 1) * 80;
        mbar_wait(bars + 8 * B_P1, 0);
        mbar_wait(bars + 8 * WB_TRIG, 0);
        mbar_expect_tx(bars + 8 * B_WST, WO_BYTES / 2);
        tma_3d(sb + OFF_WS, &m.wo, 0, 40 * r, 5 * hg, bars + 8 * B_WST);
        mbar_wait(bars + 8 * B_WST, 0);
        mbar_wait(bars + 8 * WO_TRIG, 0);
#pragma unroll 1
        for (int n = 0; n < 5; n++)
          asm volatile("cp.async.bulk.global.shared::cta.bulk_group [%0], [%1], 1280;" ::"l"(dst + 160 * n), "r"(sb + OFF_WS + 1280 * n) : "memory");
        asm volatile("cp.async.bulk.commit_group;\ncp.async.bulk.wait_group 0;\nfence.proxy.async.global;" ::: "memory");
        if (!(NOMB & 4)) asm volatile("fence.release.gpu;" ::: "memory");
        flag_bump(g_cnt + C_W + 32 * hg);
        mbar_arrive(bars + 8 * B_WOP);
        TS(71);
#pragma unroll 1
        for (int c = 0; c < 5; c++) {
          mbar_wait(bars + 8 * (B_YST + c), 0);
          asm volatile("cp.async.bulk.global.shared::cta.bulk_group [%0], [%1], 4096;\ncp.async.bulk.commit_group;"
                       ::"l"(g_Y + (5 * b + c) * Y_PITCH), "r"(sb + off_ch(c)) : "memory");
          if (c == 2) {
            asm volatile("cp.async.bulk.wait_group.read 0;" ::: "memory");
            mbar_arrive(bars + 8 * B_C34);
          }
        }
        asm volatile("cp.async.bulk.wait_group 0;\nfence.proxy.async.global;" ::: "memory");
        TS(75);
        if (!(NOMB & 2)) asm volatile("fence.release.gpu;" ::: "memory");
        flag_bump(g_cnt + C_Y + 32 * (b >> 4));
        TS(27);
        mbar_arrive(bars + 8 * B_YSIG);
        mbar_expect_tx(bars + 8 * B_YFULL, 20480);
        flag_wait(g_cnt + C_Y + 32 * hg, (lds32(sb + OFF_EPOCH) + 1) * 16);
        TS(24);
        tma_2d(sb + OFF_YT, &m.y, 128 * r, 80 * hg, bars + 8 * B_YFULL);
        tma_2d(sb + OFF_YT + 10240, &m.y, 128 * r + 64, 80 * hg, bars + 8 * B_YFULL);
      }
    }
  } else {
    asm volatile("setmaxnreg.inc.sync.aligned.u32 152;");
    if (wg < 2) {
      float acc[120];
#pragma unroll
      for (int i = 0; i < 120; i++) acc[i] = 0.f;
      const uint32_t da = desc_lo(sb + wg * 8192, 16), db = desc_lo(sb + ST_W, 8192), dc = desc_lo(sb + ST_WT, 2048);
      if (PW1) pin<120>(acc);
      if (PW1 == 2) mbar_wait(bars + 8 * B_FULL1, 0);
#pragma unroll 1
      for (int kb = 0; kb < 10; kb++) {
        mbar_wait(bars + 8 * (B_FULL1 + (kb & 3)), (kb >> 2) & 1);
        const uint32_t so = (kb & 3) * (STAGE_BYTES >> 4);
        wg_fence();
#pragma unroll
        for (int k = 0; k < 4; k++) {
          WgSST<192>::mma<HI_SW128, HI_SW128>(acc, da + so + 2 * k, db + so + 128 * k, 1);
          WgSST<48>::mma<HI_SW128, HI_SW32>(acc + 96, da + so + 2 * k, dc + so + 32 * k, 1);
        }
        wg_commit();
        wg_wait<1>();
        if (kb > 0 && lane == 0) mbar_arrive(bars + 8 * (kb == 4 ? B_E3 : B_EMPTY1 + ((kb - 1) & 3)));
      }
      mbar_wait(bars + 8 * B_EPOCH, 0);
      const uint32_t tag = lds32(sb + OFF_EPOCH) + 1;
      mbar_wait(bars + 8 * B_S3, 0);
      wg_wait<0>();
      pin<120>(acc);
      if (lane == 0) mbar_arrive(bars + 8 * B_P1);
      TSM(w == 0, 3 + wg);
      attention(acc, sb, b, wg, w, lane, tag);
    } else {
      const int tw = tid & 127, chl = 64 * (b & 1) + 8 * w + (lane >> 2);
      uint4* up = g_U + chl * U_PITCH + ((4 * (b >> 1) + (lane & 3)) ^ ((b >> 2) & 1));
      uint2 sw[10];
      uint32_t dv = 0;
      if (lane < 5) dv = __ldg(reinterpret_cast<const unsigned short*>(p.ssm_D) + 5 * b + lane);
#pragma unroll
      for (int i = 0; i < 10; i++) sw[i] = ldg64(reinterpret_cast<const uint2*>(p.shift_k) + chl + 128 * (i >> 1) + 32 * (i & 1));
      uint32_t gw[10];
#pragma unroll
      for (int i = 0; i < 10; i++) gw[i] = __ldg(reinterpret_cast<const uint32_t*>(p.gate_w) + 32 * i + lane);
      uint32_t tab[12];
      float tt[4];
      fft_tables(tab, tw);
      fft_twiddles(tt, tw);
      uint4 res[10];
#pragma unroll
      for (int i = 0; i < 10; i++) res[i] = make_uint4(0, 0, 0, 0);
      const uint32_t xa = sb + (8 * hg + 2 * w) * 128 + (((lane >> 2) ^ (2 * w)) << 4) + 4 * (lane & 3);
      float z[4] = {0.f, 0.f, 0.f, 0.f};
#pragma unroll 1
      for (int kb = 0; kb < KV_KB + 6; kb++) {
        gate_step(z, gw, sb, xa, kb, lane, p.zero);
        const int slab = kb - KV_KB - 1;
        if (slab < 0) continue;
#pragma unroll
        for (int i = 0; i < 8; i++) res[i] = res[i + 2];
        prep_slab(res + 8, sw, sb, slab, w, lane);
        TSIF(w == 0, 99 + 4 * slab);
#pragma unroll
        for (int i = 0; i < 8; i++) sw[i] = sw[i + 2];
      }
      TSIF(w == 0, 28);
      __syncwarp();
      if (lane == 0) mbar_arrive(bars + 8 * B_KVD + ((res[8].x ^ res[9].x) & p.zero));
#pragma unroll 1
      for (int kb = KV_KB + 6; kb < 8; kb++) gate_step(z, gw, sb, xa, kb, lane, p.zero);
      mbar_wait(bars + 8 * B_KVD, 0);
      fft_tables_store(tab, sb, tw);
      mbar_wait(bars + 8 * B_LAST, 0);
#pragma unroll
      for (int i = 0; i < 10; i++) up[(128 * (i >> 1) + 32 * (i & 1)) * U_PITCH] = res[i];
      __syncwarp();
      if (lane == 0) mbar_arrive(bars + 8 * B_PREP);
      TSIF(w == 0 && !U_TMA, 5);
#pragma unroll 1
      for (int kb = 8; kb < 10; kb++) gate_step(z, gw, sb, xa, kb, lane, p.zero);
      {
        const bool h = lane & 16, q = lane & 8;
        const float a = (h ? z[2] : z[0]) + __shfl_xor_sync(0xffffffffu, h ? z[0] : z[2], 16);
        const float c = (h ? z[3] : z[1]) + __shfl_xor_sync(0xffffffffu, h ? z[1] : z[3], 16);
        float y = (q ? c : a) + __shfl_xor_sync(0xffffffffu, q ? a : c, 8);
#pragma unroll
        for (int o = 4; o > 0; o >>= 1) y += __shfl_xor_sync(0xffffffffu, y, o);
        y = bf_lo(pack2(y, 0.f));
        if ((lane & 7) == 0) g_gate[16 * b + (tw >> 3)] = bf_lo(pack2(__fdividef(1.f, 1.f + __expf(-y)), 0.f));
      }
      __syncwarp();
      if (lane == 0) mbar_arrive(bars + 8 * B_GATE);
      TSIF(w == 0, 72);
      mbar_wait(bars + 8 * B_HB, 0);
      TSIF(w == 0, 2);
      const uint32_t ha = sb + U_BYTES + ((tw >> 3) * 16 + 8 + (tw & 7)) * 16;
      uint4 hv[5];
#pragma unroll
      for (int c = 0; c < 5; c++) hv[c] = lds128(ha + off_ch(c));
      __syncwarp();
#pragma unroll
      for (int c = 0; c < 5; c++) sts128((ha ^ 16) + off_ch(c), hv[c].x, hv[c].y, hv[c].z, hv[c].w);
      sts128(sb + OFF_TT + 16 * tw, __float_as_uint(tt[0]), __float_as_uint(tt[1]), __float_as_uint(tt[2]), __float_as_uint(tt[3]));
      if (tw < 5) asm volatile("st.shared.f32 [%0], %1;" ::"r"(sb + OFF_D + 4 * tw), "f"(bf_lo(dv) * 0.125f) : "memory");
      fence_async_smem();
      __syncwarp();
      if (lane == 0) mbar_arrive(bars + 8 * B_HA);
      TSIF(w == 0, 6);
    }

    FftConst fc;
    TSM(w == 0 && wg == 0, 104);
    mbar_wait(bars + 8 * B_HA, 0);
    fft_matrices(fc, sb, w, lane);
    TSM(w == 0 && wg == 0, 105);
    if (ATT_GATE && !H_EARLY) mbar_wait(bars + 8 * B_ATTN, 0);
    TSM(w == 0 && wg == 2, 124);
#pragma unroll 1
    for (uint32_t tasks = wg == 0 ? TASK0 : wg == 1 ? TASK1 : TASK2; tasks; tasks >>= 4) {
      const int c = (tasks & 7) - 1;
      conv_channel(fc, sb, c, wg, w, lane);
      if (lane == 0) mbar_arrive(bars + 8 * (B_YST + c));
      TSM(w == 0, 10 + c);
    }

    if (wg < 2) {
      const int g = lane >> 2;
      float acc[40];
#pragma unroll
      for (int i = 0; i < 40; i++) acc[i] = 0.f;
      const uint32_t da = desc_lo(sb + wg * 1024, 2048), db = desc_lo(sb, 2560);
      mbar_wait(bars + 8 * B_ATTN, 0);
      mbar_wait(bars + 8 * (B_YST + 3), 0);
      mbar_wait(bars + 8 * (B_YST + 4), 0);
      if (PW2) mbar_wait(bars + 8 * B_FULL2, 0);
      TSM(w == 0, 15 + wg);
#pragma unroll 1
      for (int j = 0; j < 8; j++) {
        mbar_wait(bars + 8 * (B_FULL2 + j), 0);
        const uint32_t oa = da + (off_o(j) >> 4), ob = db + (off_w(j) >> 4);
        wg_fence();
#pragma unroll
        for (int k = 0; k < 5; k++) WgSST<80>::mma<HI_NONE, HI_SW32>(acc, oa + 256 * k, ob + 32 * k, 1);
        wg_commit();
        wg_wait<1>();
        if (j >= 1 && j <= 4 && lane == 0) mbar_arrive(bars + 8 * (B_EMPTY2 + j - 1));
      }
      TSIF(w == 0 && wg == 0, 113);
      const int tr = 64 * wg + 16 * w + (lane & 15);
      const uint32_t fm = sb + OFF_QS + tr * 128, fx = (lane >> 4) ^ (tr & 7);
      const uint32_t ft = sb + OFF_QT + tr * 32 + (((lane >> 4) ^ (tr >> 2)) & 1) * 16;
      const float g0 = __uint_as_float(lds32(sb + OFF_GATE + (64 * wg + 16 * w + g) * 4));
      const float g1 = __uint_as_float(lds32(sb + OFF_GATE + (64 * wg + 16 * w + 8 + g) * 4));
      const uint32_t ga = pack2(g0, g0), gb = pack2(g1, g1);
      const uint32_t na = pack2(1.f - g0, 1.f - g0), nb = pack2(1.f - g1, 1.f - g1);

      wg_wait<0>();
      pin<40>(acc);
      TSM(w == 0, 17 + wg);
      uint32_t pb[20];
#pragma unroll
      for (int j = 0; j < 10; j++) {
        pb[2 * j] = bmul(na, pack2(acc[4 * j], acc[4 * j + 1]));
        pb[2 * j + 1] = bmul(nb, pack2(acc[4 * j + 2], acc[4 * j + 3]));
        asm volatile("" : "+r"(pb[2 * j]), "+r"(pb[2 * j + 1]));
      }
      const uint32_t ya = sb + OFF_YT + wg * 10240 + ((lane >> 4) * 8 + (lane & 7)) * 128 +
                          (((2 * w + (((lane >> 3) & 1) ^ wg)) ^ (lane & 7)) << 4);
      uint32_t qf[20];
      mbar_wait(bars + 8 * B_QF, 0);
#pragma unroll
      for (int j = 0; j < 5; j++) ldsm4(qf + 4 * j, j < 4 ? fm + ((fx ^ (2 * j)) << 4) : ft);
      mbar_wait(bars + 8 * B_YFULL, 0);
      TSM(w == 0 && wg == 0, 19);
#pragma unroll
      for (int j = 0; j < 5; j++) {
        uint32_t y[4];
        ldsm4t(y, ya + 2048 * j);
#pragma unroll
        for (int i = 0; i < 4; i++) qf[4 * j + i] = badd(bmul((i & 1) ? gb : ga, bmul(qf[4 * j + i], y[i])), pb[4 * j + i]);
      }
#pragma unroll
      for (int j = 0; j < 5; j++) stsm4(j < 4 ? fm + ((fx ^ (2 * j)) << 4) : ft, qf + 4 * j);
      fence_async_smem();
      __syncwarp();
      if (lane == 0) {
        const int row = 64 * wg + 16 * w;
        asm volatile("cp.async.bulk.tensor.2d.global.shared::cta.bulk_group [%0, {%2, %3}], [%1];"
                     ::"l"(&m.om), "r"(sb + OFF_QS + row * 128), "r"(80 * hg), "r"(128 * r + row) : "memory");
        asm volatile("cp.async.bulk.tensor.2d.global.shared::cta.bulk_group [%0, {%2, %3}], [%1];"
                     ::"l"(&m.ot), "r"(sb + OFF_QT + row * 32), "r"(80 * hg + 64), "r"(128 * r + row) : "memory");
        asm volatile("cp.async.bulk.commit_group;\ncp.async.bulk.wait_group.read 0;" ::: "memory");
      }
      TSM(true, 40 + 4 * wg + w);
      if (ENDBAR) asm volatile("bar.sync 15, 256;" ::: "memory");
    }
  }
}

typedef CUresult (*EncodeFn)(CUtensorMap*, CUtensorMapDataType, cuuint32_t, void*, const cuuint64_t*, const cuuint64_t*,
                             const cuuint32_t*, const cuuint32_t*, CUtensorMapInterleave, CUtensorMapSwizzle,
                             CUtensorMapL2promotion, CUtensorMapFloatOOBfill);

void encode(EncodeFn fn, CUtensorMap* tm, const void* base, int rank, const cuuint64_t* dims, const cuuint64_t* strides,
            const cuuint32_t* box, CUtensorMapSwizzle swz) {
  const cuuint32_t ones[3] = {1, 1, 1};
  fn(tm, CU_TENSOR_MAP_DATA_TYPE_BFLOAT16, rank, const_cast<void*>(base), dims, strides, box, ones,
     CU_TENSOR_MAP_INTERLEAVE_NONE, swz, CU_TENSOR_MAP_L2_PROMOTION_L2_128B, CU_TENSOR_MAP_FLOAT_OOB_FILL_NONE);
}

}

extern "C" void kernel_launch(void* const* d_in, const int* in_sizes, int n_in, void* d_out, int out_size) {
  (void)in_sizes; (void)n_in; (void)out_size;
  Params p;
  p.q = (const __nv_bfloat16*)d_in[0];
  p.k = (const __nv_bfloat16*)d_in[1];
  p.v = (const __nv_bfloat16*)d_in[2];
  p.shift_k = (const __nv_bfloat16*)d_in[3];
  p.ssm_k = (const __nv_bfloat16*)d_in[4];
  p.ssm_D = (const __nv_bfloat16*)d_in[5];
  p.wqkv = (const __nv_bfloat16*)d_in[7];
  p.wo = (const __nv_bfloat16*)d_in[8];
  p.gate_w = (const __nv_bfloat16*)d_in[9];
  p.out = (__nv_bfloat16*)d_out;
  p.zero = 0;

  static EncodeFn fn = nullptr;
  static void *yaddr = nullptr, *uaddr = nullptr;
  if (!fn) {
    cudaDriverEntryPointQueryResult qr;
    void* f = nullptr;
    cudaGetDriverEntryPoint("cuTensorMapEncodeTiled", &f, cudaEnableDefault, &qr);
    fn = (EncodeFn)f;
    cudaGetSymbolAddress(&yaddr, g_Y);
    cudaGetSymbolAddress(&uaddr, g_U);
    cudaFuncSetAttribute(fused_kernel, cudaFuncAttributeMaxDynamicSharedMemorySize, SMEM_BYTES);
  }
  Maps m;
  {
    const cuuint64_t dims[3] = {640, 1024, 2}, st[2] = {2560, 1280};
    const cuuint32_t box[3] = {64, 64, 2};
    encode(fn, &m.x, p.q, 3, dims, st, box, CU_TENSOR_MAP_SWIZZLE_128B);
  }
  {
    const cuuint64_t dims[3] = {640, 640, 3}, st[2] = {3840, 1280};
    const cuuint32_t box[3] = {64, 64, 3}, boxt[3] = {16, 64, 3};
    encode(fn, &m.wm, p.wqkv, 3, dims, st, box, CU_TENSOR_MAP_SWIZZLE_128B);
    encode(fn, &m.wt, p.wqkv, 3, dims, st, boxt, CU_TENSOR_MAP_SWIZZLE_32B);
  }
  {
    const cuuint64_t dims[3] = {64, 2048, 10}, st[2] = {1280, 128};
    const cuuint32_t boxk[3] = {64, 35, 1}, boxv[3] = {64, 32, 1};
    encode(fn, &m.k, p.k, 3, dims, st, boxk, CU_TENSOR_MAP_SWIZZLE_128B);
    encode(fn, &m.v, p.v, 3, dims, st, boxv, CU_TENSOR_MAP_SWIZZLE_128B);
  }
  {
    const cuuint64_t dims[3] = {16, 640, 40}, st[2] = {1280, 32};
    const cuuint32_t box[3] = {16, 40, 5};
    encode(fn, &m.wo, p.wo, 3, dims, st, box, CU_TENSOR_MAP_SWIZZLE_32B);
  }
  {
    const cuuint64_t dims[2] = {2048, 640}, st[1] = {Y_PITCH * 16};
    const cuuint32_t box[2] = {64, 80};
    encode(fn, &m.y, yaddr, 2, dims, st, box, CU_TENSOR_MAP_SWIZZLE_128B);
    const cuuint64_t stu[1] = {U_PITCH * 16};
    const cuuint32_t boxu[2] = {32, 64};
    encode(fn, &m.u, uaddr, 2, dims, stu, boxu, CU_TENSOR_MAP_SWIZZLE_NONE);
  }
  {
    const cuuint64_t dims[2] = {640, 2048}, st[1] = {1280};
    const cuuint32_t bqm[2] = {64, 128}, bqt[2] = {16, 128}, bom[2] = {64, 16}, bot[2] = {16, 16};
    encode(fn, &m.qm, p.q, 2, dims, st, bqm, CU_TENSOR_MAP_SWIZZLE_128B);
    encode(fn, &m.qt, p.q, 2, dims, st, bqt, CU_TENSOR_MAP_SWIZZLE_32B);
    encode(fn, &m.om, p.out, 2, dims, st, bom, CU_TENSOR_MAP_SWIZZLE_128B);
    encode(fn, &m.ot, p.out, 2, dims, st, bot, CU_TENSOR_MAP_SWIZZLE_32B);
  }
  fused_kernel<<<NCTA, NTHR, SMEM_BYTES>>>(m, p);
}
```

```cpp
#include <cuda.h>
#include <cuda_bf16.h>
#include <cuda_runtime.h>
#include <stdint.h>

namespace {

constexpr int SEQ = 2048, DIM = 640, NCTA = 128, NTHR = 512;

#define TRIG_KB 9
#define KV_KB 2
#define DEV_EXIT 0
#define ATT_GATE 1
#define FENCE_LO 0
#define FENCE_HI 0
#define PW1 2
#define PW2 1
#define ENDBAR 0
#define PAD_KB 0
#define Y_ALIAS 1
#define H_EARLY 1
#define NOMB 0
#define SRC_ROT 0
#define WAIT_NS 0
#define WB_TRIG B_USIG
#define TAILF 1
#define T_ISSUE 384
#define T_PF 416
#define T_INIT 448
#define ATT_MERGE 0
#define BMAP 1
#define PRE2 1
#define KV_MIX 0
#define O_DEFER 0
#define TASK0 0x52
#define TASK1 0x3
#define TASK2 0x41
#define HALO_FIRST 1
#define PREV_EARLY 0
#define G_LAG 0
#define ACQ 0
#define U_TMA 0
#define U_GATE 0
#define RF_GATE 0
#define WO_TRIG B_WST
#define WL_TRIG B_WOP
#define WO_GATE 1

constexpr uint32_t STAGE_BYTES = 47104, ST_W = 16384, ST_WT = 40960;
constexpr uint32_t O_BYTES = 20480, WO_BYTES = 12800;
constexpr uint32_t OFF_OA = 0;
constexpr uint32_t OFF_QS = 3 * O_BYTES, OFF_QT = OFF_QS + 16384;
constexpr uint32_t OFF_WC = 81920;
constexpr uint32_t OFF_WA = 94720;
constexpr uint32_t OFF_GATE = 145920;
constexpr uint32_t OFF_TT = 146432;
constexpr uint32_t OFF_KVX = 148480;
constexpr uint32_t OFF_CH3 = 163840;
constexpr uint32_t CH_BYTES = 12288, U_BYTES = 4096;
constexpr uint32_t OFF_FT = 225280, OFF_GT = 229376;
constexpr uint32_t OFF_CH0 = 188416;
constexpr uint32_t OFF_KVS = OFF_CH0, KVS_V = 4480, KVS_BYTES = 8576;
constexpr uint32_t OFF_WS = OFF_WA;
__device__ __forceinline__ uint32_t off_us(int s) { return OFF_CH0 + 4096 * ((0x65320 >> (4 * s)) & 7); }
constexpr uint32_t OFF_YT = 163840;
constexpr uint32_t OFF_BAR = 231936;
constexpr uint32_t SMEM_BYTES = OFF_BAR + 512;

enum : uint32_t {
  B_FULL1 = 0, B_EMPTY1 = 4, B_S3 = 7, B_FULL2 = 52, B_EMPTY2 = 13, B_U = 8, B_GATE = 12, B_HA = 19, B_HB = 20,
  B_ATTN = 21, B_C34 = 22, B_CONV = 23, B_YFULL = 24, B_EPOCH = 25, B_PREP = 26, B_P1 = 27, B_LAST = 28,
  B_E3 = 29, B_OSIG = 30, B_WOP = 31, B_USIG = 32, B_WST = 33, B_KV = 34, B_KVD = 39, B_QF = 17, B_YST = 40,
  B_US = 45, B_YSIG = 50
};
constexpr uint32_t OFF_EPOCH = OFF_BAR + 8 * 51, OFF_D = OFF_BAR + 8 * 60;
__device__ __forceinline__ uint32_t off_o(int j) { return j < 4 ? OFF_OA + j * O_BYTES : j < 6 ? OFF_CH0 + (j - 4) * O_BYTES : OFF_OA + (j - 6) * O_BYTES; }
__device__ __forceinline__ uint32_t off_w(int j) { return j < 4 ? OFF_WA + j * WO_BYTES : j == 4 ? OFF_KVX : j == 5 ? OFF_WC : OFF_WA + (j - 6) * WO_BYTES; }
__device__ __forceinline__ int step_src(int hg, int j) { return SRC_ROT ? (hg + j) & 7 : j == 0 ? hg : j <= hg ? j - 1 : j; }
__device__ __forceinline__ bool tail_first(int hg) { return TAILF && (hg & 3) == 3; }
__device__ __forceinline__ uint32_t off_ch(int c) { return (c < 3 ? OFF_CH0 : OFF_CH3 - 3 * CH_BYTES) + c * CH_BYTES; }

#define U_PITCH 264
__device__ __align__(1024) uint4 g_U[DIM * U_PITCH];
__device__ uint4 g_O[NCTA * 1280];
#define g_Y g_U
constexpr int Y_PITCH = U_PITCH;
__device__ uint4 g_WO[64 * 800];
__device__ uint4 g_halo[NCTA * 2 * 7 * 32];
__device__ float g_gate[SEQ + PAD_KB * 256];
__device__ unsigned g_cnt[32 * (1 + 2 * 16 + 8 + NCTA)];
constexpr int C_LAUNCH = 0, C_PREP = 32, C_Y = 32 * 17, C_W = 32 * 33, C_O = 32 * 41;

#define TSM(cond, slot) do { } while (0)
#define TSIF(cond, slot) do { if (__LINE__ >= FENCE_LO && __LINE__ < FENCE_HI) sched_fence(); } while (0)
__device__ __forceinline__ void sched_fence() {
  asm volatile("{\n.reg .pred p;\n.reg .u32 c;\nmov.u32 c, %%clock;\nsetp.eq.u32 p, c, 0;\n@p st.shared.u32 [%0], c;\n}"
               ::"r"(1024 + OFF_EPOCH + 4) : "memory");
}
#define TS(slot) TSIF(true, slot)

struct Params {
  const __nv_bfloat16 *q, *k, *v, *shift_k, *ssm_k, *ssm_D, *wqkv, *wo, *gate_w;
  __nv_bfloat16* out;
  uint32_t zero;
};

#define POLL_NS 0
constexpr int SPIN_LIMIT = 1 << 17;

__device__ __forceinline__ void mbar_init(uint32_t bar, uint32_t count) {
  asm volatile("mbarrier.init.shared::cta.b64 [%0], %1;" ::"r"(bar), "r"(count) : "memory");
}
__device__ __forceinline__ void mbar_expect_tx(uint32_t bar, uint32_t bytes) {
  asm volatile("mbarrier.arrive.expect_tx.shared::cta.b64 _, [%0], %1;" ::"r"(bar), "r"(bytes) : "memory");
}
__device__ __forceinline__ void mbar_arrive(uint32_t bar) {
  asm volatile("mbarrier.arrive.shared::cta.b64 _, [%0];" ::"r"(bar) : "memory");
}
__device__ __forceinline__ void mbar_wait(uint32_t bar, uint32_t parity) {
  uint32_t ok;
  int spins = 0;
  do {
    if (WAIT_NS)
      asm volatile("{\n.reg .pred p;\nmbarrier.try_wait.parity.shared::cta.b64 p, [%1], %2, %3;\nselp.b32 %0, 1, 0, p;\n}"
                   : "=r"(ok) : "r"(bar), "r"(parity), "r"(WAIT_NS) : "memory");
    else
      asm volatile("{\n.reg .pred p;\nmbarrier.try_wait.parity.shared::cta.b64 p, [%1], %2;\nselp.b32 %0, 1, 0, p;\n}"
                   : "=r"(ok) : "r"(bar), "r"(parity) : "memory");
    if (++spins > SPIN_LIMIT) break;
  } while (!ok);
}
__device__ __forceinline__ unsigned flag_read(const unsigned* p) {
  unsigned v;
  asm volatile("ld.relaxed.gpu.global.u32 %0, [%1];" : "=r"(v) : "l"(p) : "memory");
  return v;
}
__device__ __forceinline__ void flag_poll(const unsigned* p, unsigned target) {
  unsigned v;
  int spins = 0;
  do {
    if (POLL_NS && spins) __nanosleep(POLL_NS);
    asm volatile("ld.relaxed.gpu.global.u32 %0, [%1];" : "=r"(v) : "l"(p) : "memory");
    if (++spins > SPIN_LIMIT) break;
  } while ((int)(v - target) < 0);
}
__device__ __forceinline__ void flag_wait(const unsigned* p, unsigned target) {
  flag_poll(p, target);
  if (ACQ) asm volatile("fence.acquire.gpu;\nfence.proxy.async.global;" ::: "memory");
}
__device__ __forceinline__ void flag_signal(unsigned* p, int n, int lane) {
  if (lane == 0) asm volatile("fence.release.gpu;" ::: "memory");
  __syncwarp();
  if (lane < n) asm volatile("red.relaxed.gpu.global.add.u32 [%0], 1;" ::"l"(p + 32 * lane) : "memory");
}
__device__ __forceinline__ void flag_bump(unsigned* p) {
  asm volatile("red.relaxed.gpu.global.add.u32 [%0], 1;" ::"l"(p) : "memory");
}
__device__ __forceinline__ void fence_async_smem() { asm volatile("fence.proxy.async.shared::cta;" ::: "memory"); }
__device__ __forceinline__ void wg_sync(int id) { asm volatile("bar.sync %0, 128;" ::"r"(id) : "memory"); }

__device__ __forceinline__ void tma_2d(uint32_t dst, const CUtensorMap* tm, int c0, int c1, uint32_t bar) {
  asm volatile("cp.async.bulk.tensor.2d.shared::cluster.global.mbarrier::complete_tx::bytes [%0], [%1, {%3, %4}], [%2];"
               ::"r"(dst), "l"(tm), "r"(bar), "r"(c0), "r"(c1) : "memory");
}
__device__ __forceinline__ void tma_3d(uint32_t dst, const CUtensorMap* tm, int c0, int c1, int c2, uint32_t bar) {
  asm volatile("cp.async.bulk.tensor.3d.shared::cluster.global.mbarrier::complete_tx::bytes [%0], [%1, {%3, %4, %5}], [%2];"
               ::"r"(dst), "l"(tm), "r"(bar), "r"(c0), "r"(c1), "r"(c2) : "memory");
}
__device__ __forceinline__ void bulk_load(uint32_t dst, const void* src, uint32_t bytes, uint32_t bar) {
  asm volatile("cp.async.bulk.shared::cluster.global.mbarrier::complete_tx::bytes [%0], [%1], %2, [%3];"
               ::"r"(dst), "l"(src), "r"(bytes), "r"(bar) : "memory");
}
__device__ __forceinline__ void tm_prefetch(const CUtensorMap* tm) {
  asm volatile("prefetch.tensormap [%0];" ::"l"(tm) : "memory");
}

__device__ __forceinline__ void wg_fence() { asm volatile("wgmma.fence.sync.aligned;" ::: "memory"); }
__device__ __forceinline__ void wg_commit() { asm volatile("wgmma.commit_group.sync.aligned;" ::: "memory"); }
template <int N> __device__ __forceinline__ void wg_wait() { asm volatile("wgmma.wait_group.sync.aligned %0;" ::"n"(N) : "memory"); }
__device__ __forceinline__ uint32_t desc_lo(uint32_t addr, uint32_t lbo) { return ((addr & 0x3FFFF) >> 4) | ((lbo >> 4) << 16); }
constexpr uint32_t desc_hi(uint32_t sbo, uint32_t swz) { return (sbo >> 4) | (swz << 30); }
constexpr uint32_t HI_SW128 = desc_hi(1024, 1), HI_SW64 = desc_hi(512, 2), HI_SW32 = desc_hi(256, 3), HI_NONE = desc_hi(128, 0);
template <int N> __device__ __forceinline__ void pin(float* d) {
#pragma unroll
  for (int i = 0; i < N; i++) asm volatile("" : "+f"(d[i])::"memory");
}

__device__ __forceinline__ uint32_t lds32(uint32_t a) {
  uint32_t v;
  asm volatile("ld.volatile.shared.u32 %0, [%1];" : "=r"(v) : "r"(a) : "memory");
  return v;
}
__device__ __forceinline__ uint4 ldg128(const void* a) {
  uint4 v;
  asm volatile("ld.global.nc.v4.u32 {%0, %1, %2, %3}, [%4];" : "=r"(v.x), "=r"(v.y), "=r"(v.z), "=r"(v.w) : "l"(a) : "memory");
  return v;
}
__device__ __forceinline__ uint2 ldg64(const void* a) {
  uint2 v;
  asm volatile("ld.global.nc.v2.u32 {%0, %1}, [%2];" : "=r"(v.x), "=r"(v.y) : "l"(a) : "memory");
  return v;
}
__device__ __forceinline__ void ldsm4(uint32_t* r, uint32_t a) {
  asm volatile("ldmatrix.sync.aligned.m8n8.x4.shared.b16 {%0, %1, %2, %3}, [%4];"
               : "=r"(r[0]), "=r"(r[1]), "=r"(r[2]), "=r"(r[3]) : "r"(a) : "memory");
}
__device__ __forceinline__ void ldsm4t(uint32_t* r, uint32_t a) {
  asm volatile("ldmatrix.sync.aligned.m8n8.x4.trans.shared.b16 {%0, %1, %2, %3}, [%4];"
               : "=r"(r[0]), "=r"(r[1]), "=r"(r[2]), "=r"(r[3]) : "r"(a) : "memory");
}
__device__ __forceinline__ uint4 lds128(uint32_t a) {
  uint4 v;
  asm volatile("ld.shared.v4.u32 {%0, %1, %2, %3}, [%4];" : "=r"(v.x), "=r"(v.y), "=r"(v.z), "=r"(v.w) : "r"(a) : "memory");
  return v;
}
__device__ __forceinline__ void sts128(uint32_t a, uint32_t x, uint32_t y, uint32_t z, uint32_t w) {
  asm volatile("st.shared.v4.u32 [%0], {%1, %2, %3, %4};" ::"r"(a), "r"(x), "r"(y), "r"(z), "r"(w) : "memory");
}
__device__ __forceinline__ void stsm4(uint32_t a, const uint32_t* r) {
  asm volatile("stmatrix.sync.aligned.m8n8.x4.shared.b16 [%0], {%1, %2, %3, %4};" ::"r"(a), "r"(r[0]), "r"(r[1]), "r"(r[2]), "r"(r[3]) : "memory");
}
__device__ __forceinline__ void stsm4t(uint32_t a, const uint32_t* r) {
  asm volatile("stmatrix.sync.aligned.m8n8.x4.trans.shared.b16 [%0], {%1, %2, %3, %4};" ::"r"(a), "r"(r[0]), "r"(r[1]), "r"(r[2]), "r"(r[3]) : "memory");
}
__device__ __forceinline__ uint32_t pack2(float lo, float hi) {
  uint32_t r;
  asm("cvt.rn.bf16x2.f32 %0, %1, %2;" : "=r"(r) : "f"(hi), "f"(lo));
  return r;
}
__device__ __forceinline__ uint32_t movm(uint32_t a) {
  uint32_t d;
  asm volatile("movmatrix.sync.aligned.m8n8.trans.b16 %0, %1;" : "=r"(d) : "r"(a));
  return d;
}
__device__ __forceinline__ uint32_t bmul(uint32_t a, uint32_t b) {
  uint32_t d;
  asm("mul.rn.bf16x2 %0, %1, %2;" : "=r"(d) : "r"(a), "r"(b));
  return d;
}
__device__ __forceinline__ uint32_t badd(uint32_t a, uint32_t b) {
  uint32_t d;
  asm("add.rn.bf16x2 %0, %1, %2;" : "=r"(d) : "r"(a), "r"(b));
  return d;
}
__device__ __forceinline__ float bf_lo(uint32_t x) { return __uint_as_float(x << 16); }
__device__ __forceinline__ float bf_hi(uint32_t x) { return __uint_as_float(x & 0xFFFF0000u); }
__device__ __forceinline__ float ex2(float x) {
  float y;
  asm("ex2.approx.ftz.f32 %0, %1;" : "=f"(y) : "f"(x));
  return y;
}
__device__ __forceinline__ float rcp(float x) {
  float y;
  asm("rcp.approx.ftz.f32 %0, %1;" : "=f"(y) : "f"(x));
  return y;
}
__device__ __forceinline__ void mma16816(float* d, uint32_t a0, uint32_t a1, uint32_t a2, uint32_t a3, uint32_t b0, uint32_t b1) {
  asm volatile("mma.sync.aligned.m16n8k16.row.col.f32.bf16.bf16.f32 {%0, %1, %2, %3}, {%4, %5, %6, %7}, {%8, %9}, {%0, %1, %2, %3};"
               : "+f"(d[0]), "+f"(d[1]), "+f"(d[2]), "+f"(d[3])
               : "r"(a0), "r"(a1), "r"(a2), "r"(a3), "r"(b0), "r"(b1));
}
__device__ __forceinline__ void mma1688(float* d, uint32_t a0, uint32_t a1, uint32_t b0) {
  asm volatile("mma.sync.aligned.m16n8k8.row.col.f32.bf16.bf16.f32 {%0, %1, %2, %3}, {%4, %5}, {%6}, {%0, %1, %2, %3};"
               : "+f"(d[0]), "+f"(d[1]), "+f"(d[2]), "+f"(d[3])
               : "r"(a0), "r"(a1), "r"(b0));
}

template <int N> struct WgRS;
template <int N> struct WgSST;
template <> struct WgRS<32> {
  template <uint32_t HB>
  static __device__ __forceinline__ void mma(float* d, const uint32_t* a, uint32_t db) {
    asm volatile("{\n.reg .pred p;\n.reg .b64 db;\nsetp.ne.b32 p, %22, 0;\n"
      "mov.b64 db, {%20, %21};\n"
      "wgmma.mma_async.sync.aligned.m64n32k16.f32.bf16.bf16 {"
      "%0, %1, %2, %3, %4, %5, %6, %7, %8, %9, %10, %11, %12, %13, %14, %15"
      "}, {%16, %17, %18, %19}, db, p, 1, 1, 1;\n}\n"
      : "+f"(d[0]), "+f"(d[1]), "+f"(d[2]), "+f"(d[3]), "+f"(d[4]), "+f"(d[5]), "+f"(d[6]), "+f"(d[7]),
        "+f"(d[8]), "+f"(d[9]), "+f"(d[10]), "+f"(d[11]), "+f"(d[12]), "+f"(d[13]), "+f"(d[14]), "+f"(d[15])
      : "r"(a[0]), "r"(a[1]), "r"(a[2]), "r"(a[3]), "r"(db), "n"(HB), "n"(1));
  }
  template <uint32_t HB>
  static __device__ __forceinline__ void set(float* d, const uint32_t* a, uint32_t db) {
    asm volatile("{\n.reg .pred p;\n.reg .b64 db;\nsetp.ne.b32 p, %22, 0;\n"
      "mov.b64 db, {%20, %21};\n"
      "wgmma.mma_async.sync.aligned.m64n32k16.f32.bf16.bf16 {"
      "%0, %1, %2, %3, %4, %5, %6, %7, %8, %9, %10, %11, %12, %13, %14, %15"
      "}, {%16, %17, %18, %19}, db, p, 1, 1, 1;\n}\n"
      : "=f"(d[0]), "=f"(d[1]), "=f"(d[2]), "=f"(d[3]), "=f"(d[4]), "=f"(d[5]), "=f"(d[6]), "=f"(d[7]),
        "=f"(d[8]), "=f"(d[9]), "=f"(d[10]), "=f"(d[11]), "=f"(d[12]), "=f"(d[13]), "=f"(d[14]), "=f"(d[15])
      : "r"(a[0]), "r"(a[1]), "r"(a[2]), "r"(a[3]), "r"(db), "n"(HB), "n"(0));
  }
};
template <> struct WgRS<64> {
  template <uint32_t HB>
  static __device__ __forceinline__ void mma(float* d, const uint32_t* a, uint32_t db) {
    asm volatile("{\n.reg .pred p;\n.reg .b64 db;\nsetp.ne.b32 p, %38, 0;\n"
      "mov.b64 db, {%36, %37};\n"
      "wgmma.mma_async.sync.aligned.m64n64k16.f32.bf16.bf16 {"
      "%0, %1, %2, %3, %4, %5, %6, %7, %8, %9, %10, %11, %12, %13, %14, %15, "
      "%16, %17, %18, %19, %20, %21, %22, %23, %24, %25, %26, %27, %28, %29, %30, %31"
      "}, {%32, %33, %34, %35}, db, p, 1, 1, 1;\n}\n"
      : "+f"(d[0]), "+f"(d[1]), "+f"(d[2]), "+f"(d[3]), "+f"(d[4]), "+f"(d[5]), "+f"(d[6]), "+f"(d[7]),
        "+f"(d[8]), "+f"(d[9]), "+f"(d[10]), "+f"(d[11]), "+f"(d[12]), "+f"(d[13]), "+f"(d[14]), "+f"(d[15]),
        "+f"(d[16]), "+f"(d[17]), "+f"(d[18]), "+f"(d[19]), "+f"(d[20]), "+f"(d[21]), "+f"(d[22]), "+f"(d[23]),
        "+f"(d[24]), "+f"(d[25]), "+f"(d[26]), "+f"(d[27]), "+f"(d[28]), "+f"(d[29]), "+f"(d[30]), "+f"(d[31])
      : "r"(a[0]), "r"(a[1]), "r"(a[2]), "r"(a[3]), "r"(db), "n"(HB), "n"(1));
  }
  template <uint32_t HB>
  static __device__ __forceinline__ void set(float* d, const uint32_t* a, uint32_t db) {
    asm volatile("{\n.reg .pred p;\n.reg .b64 db;\nsetp.ne.b32 p, %38, 0;\n"
      "mov.b64 db, {%36, %37};\n"
      "wgmma.mma_async.sync.aligned.m64n64k16.f32.bf16.bf16 {"
      "%0, %1, %2, %3, %4, %5, %6, %7, %8, %9, %10, %11, %12, %13, %14, %15, "
      "%16, %17, %18, %19, %20, %21, %22, %23, %24, %25, %26, %27, %28, %29, %30, %31"
      "}, {%32, %33, %34, %35}, db, p, 1, 1, 1;\n}\n"
      : "=f"(d[0]), "=f"(d[1]), "=f"(d[2]), "=f"(d[3]), "=f"(d[4]), "=f"(d[5]), "=f"(d[6]), "=f"(d[7]),
        "=f"(d[8]), "=f"(d[9]), "=f"(d[10]), "=f"(d[11]), "=f"(d[12]), "=f"(d[13]), "=f"(d[14]), "=f"(d[15]),
        "=f"(d[16]), "=f"(d[17]), "=f"(d[18]), "=f"(d[19]), "=f"(d[20]), "=f"(d[21]), "=f"(d[22]), "=f"(d[23]),
        "=f"(d[24]), "=f"(d[25]), "=f"(d[26]), "=f"(d[27]), "=f"(d[28]), "=f"(d[29]), "=f"(d[30]), "=f"(d[31])
      : "r"(a[0]), "r"(a[1]), "r"(a[2]), "r"(a[3]), "r"(db), "n"(HB), "n"(0));
  }
};
template <> struct WgSST<48> {
  template <uint32_t HA, uint32_t HB>
  static __device__ __forceinline__ void mma(float* d, uint32_t da, uint32_t db, int sc) {
    asm volatile("{\n.reg .pred p;\n.reg .b64 da, db;\nsetp.ne.b32 p, %28, 0;\n"
      "mov.b64 da, {%24, %25};\nmov.b64 db, {%26, %27};\n"
      "wgmma.mma_async.sync.aligned.m64n48k16.f32.bf16.bf16 {"
      "%0, %1, %2, %3, %4, %5, %6, %7, %8, %9, %10, %11, %12, %13, %14, %15, "
      "%16, %17, %18, %19, %20, %21, %22, %23"
      "}, da, db, p, 1, 1, 0, 1;\n}\n"
      : "+f"(d[0]), "+f"(d[1]), "+f"(d[2]), "+f"(d[3]), "+f"(d[4]), "+f"(d[5]), "+f"(d[6]), "+f"(d[7]),
        "+f"(d[8]), "+f"(d[9]), "+f"(d[10]), "+f"(d[11]), "+f"(d[12]), "+f"(d[13]), "+f"(d[14]), "+f"(d[15]),
        "+f"(d[16]), "+f"(d[17]), "+f"(d[18]), "+f"(d[19]), "+f"(d[20]), "+f"(d[21]), "+f"(d[22]), "+f"(d[23])
      : "r"(da), "n"(HA), "r"(db), "n"(HB), "r"(sc));
  }
};
template <> struct WgSST<80> {
  template <uint32_t HA, uint32_t HB>
  static __device__ __forceinline__ void mma(float* d, uint32_t da, uint32_t db, int sc) {
    asm volatile("{\n.reg .pred p;\n.reg .b64 da, db;\nsetp.ne.b32 p, %44, 0;\n"
      "mov.b64 da, {%40, %41};\nmov.b64 db, {%42, %43};\n"
      "wgmma.mma_async.sync.aligned.m64n80k16.f32.bf16.bf16 {"
      "%0, %1, %2, %3, %4, %5, %6, %7, %8, %9, %10, %11, %12, %13, %14, %15, "
      "%16, %17, %18, %19, %20, %21, %22, %23, %24, %25, %26, %27, %28, %29, %30, %31, "
      "%32, %33, %34, %35, %36, %37, %38, %39"
      "}, da, db, p, 1, 1, 0, 1;\n}\n"
      : "+f"(d[0]), "+f"(d[1]), "+f"(d[2]), "+f"(d[3]), "+f"(d[4]), "+f"(d[5]), "+f"(d[6]), "+f"(d[7]),
        "+f"(d[8]), "+f"(d[9]), "+f"(d[10]), "+f"(d[11]), "+f"(d[12]), "+f"(d[13]), "+f"(d[14]), "+f"(d[15]),
        "+f"(d[16]), "+f"(d[17]), "+f"(d[18]), "+f"(d[19]), "+f"(d[20]), "+f"(d[21]), "+f"(d[22]), "+f"(d[23]),
        "+f"(d[24]), "+f"(d[25]), "+f"(d[26]), "+f"(d[27]), "+f"(d[28]), "+f"(d[29]), "+f"(d[30]), "+f"(d[31]),
        "+f"(d[32]), "+f"(d[33]), "+f"(d[34]), "+f"(d[35]), "+f"(d[36]), "+f"(d[37]), "+f"(d[38]), "+f"(d[39])
      : "r"(da), "n"(HA), "r"(db), "n"(HB), "r"(sc));
  }
};
template <> struct WgSST<192> {
  template <uint32_t HA, uint32_t HB>
  static __device__ __forceinline__ void mma(float* d, uint32_t da, uint32_t db, int sc) {
    asm volatile("{\n.reg .pred p;\n.reg .b64 da, db;\nsetp.ne.b32 p, %100, 0;\n"
      "mov.b64 da, {%96, %97};\nmov.b64 db, {%98, %99};\n"
      "wgmma.mma_async.sync.aligned.m64n192k16.f32.bf16.bf16 {"
      "%0, %1, %2, %3, %4, %5, %6, %7, %8, %9, %10, %11, %12, %13, %14, %15, "
      "%16, %17, %18, %19, %20, %21, %22, %23, %24, %25, %26, %27, %28, %29, %30, %31, "
      "%32, %33, %34, %35, %36, %37, %38, %39, %40, %41, %42, %43, %44, %45, %46, %47, "
      "%48, %49, %50, %51, %52, %53, %54, %55, %56, %57, %58, %59, %60, %61, %62, %63, "
      "%64, %65, %66, %67, %68, %69, %70, %71, %72, %73, %74, %75, %76, %77, %78, %79, "
      "%80, %81, %82, %83, %84, %85, %86, %87, %88, %89, %90, %91, %92, %93, %94, %95"
      "}, da, db, p, 1, 1, 0, 1;\n}\n"
      : "+f"(d[0]), "+f"(d[1]), "+f"(d[2]), "+f"(d[3]), "+f"(d[4]), "+f"(d[5]), "+f"(d[6]), "+f"(d[7]),
        "+f"(d[8]), "+f"(d[9]), "+f"(d[10]), "+f"(d[11]), "+f"(d[12]), "+f"(d[13]), "+f"(d[14]), "+f"(d[15]),
        "+f"(d[16]), "+f"(d[17]), "+f"(d[18]), "+f"(d[19]), "+f"(d[20]), "+f"(d[21]), "+f"(d[22]), "+f"(d[23]),
        "+f"(d[24]), "+f"(d[25]), "+f"(d[26]), "+f"(d[27]), "+f"(d[28]), "+f"(d[29]), "+f"(d[30]), "+f"(d[31]),
        "+f"(d[32]), "+f"(d[33]), "+f"(d[34]), "+f"(d[35]), "+f"(d[36]), "+f"(d[37]), "+f"(d[38]), "+f"(d[39]),
        "+f"(d[40]), "+f"(d[41]), "+f"(d[42]), "+f"(d[43]), "+f"(d[44]), "+f"(d[45]), "+f"(d[46]), "+f"(d[47]),
        "+f"(d[48]), "+f"(d[49]), "+f"(d[50]), "+f"(d[51]), "+f"(d[52]), "+f"(d[53]), "+f"(d[54]), "+f"(d[55]),
        "+f"(d[56]), "+f"(d[57]), "+f"(d[58]), "+f"(d[59]), "+f"(d[60]), "+f"(d[61]), "+f"(d[62]), "+f"(d[63]),
        "+f"(d[64]), "+f"(d[65]), "+f"(d[66]), "+f"(d[67]), "+f"(d[68]), "+f"(d[69]), "+f"(d[70]), "+f"(d[71]),
        "+f"(d[72]), "+f"(d[73]), "+f"(d[74]), "+f"(d[75]), "+f"(d[76]), "+f"(d[77]), "+f"(d[78]), "+f"(d[79]),
        "+f"(d[80]), "+f"(d[81]), "+f"(d[82]), "+f"(d[83]), "+f"(d[84]), "+f"(d[85]), "+f"(d[86]), "+f"(d[87]),
        "+f"(d[88]), "+f"(d[89]), "+f"(d[90]), "+f"(d[91]), "+f"(d[92]), "+f"(d[93]), "+f"(d[94]), "+f"(d[95])
      : "r"(da), "n"(HA), "r"(db), "n"(HB), "r"(sc));
  }
};

struct FftConst {
  uint32_t f[2][4], fi[4][4];
  float ta[4], tb[4];
};
__device__ __forceinline__ void cis(int m, float scale, float& c, float& s) {
  const float a = (float)m * (-6.283185307179586f * scale);
  c = __cosf(a);
  s = __sinf(a);
}
__device__ __forceinline__ void fft_tables(uint32_t (&v)[12], int tw) {
  const int row = tw >> 2, ch = tw & 3;
#pragma unroll
  for (int i = 0; i < 4; i++) {
    float c[2], s[2], x[2];
#pragma unroll
    for (int e = 0; e < 2; e++) {
      cis((((32 * (8 * ch + 2 * i + e) + 15) * (4 * row - 63) + 2048) & 4095) - 2048, 1.f / 4096, c[e], s[e]);
      float gc, gs;
      cis((((row & 15) * (8 * (ch & 1) + 2 * i + e) + 8) & 15) - 8, 1.f / 16, gc, gs);
      x[e] = (row >> 4) == (ch >> 1) ? gc : (ch >> 1) ? gs : -gs;
    }
    v[i] = pack2(c[0] * 0.125f, c[1] * 0.125f);
    v[4 + i] = pack2(s[0] * 0.125f, s[1] * 0.125f);
    v[8 + i] = pack2(x[0], x[1]);
  }
#pragma unroll
  for (int i = 0; i < 12; i++) asm volatile("" : "+r"(v[i]));
}
__device__ __forceinline__ void fft_tables_store(const uint32_t (&v)[12], uint32_t sb, int tw) {
  const int row = tw >> 2;
  const uint32_t x = ((tw ^ (row >> 1)) & 3) << 4, a = sb + OFF_FT + (16 * (row >> 3) + (row & 7)) * 64 + x;
  sts128(a, v[0], v[1], v[2], v[3]);
  sts128(a + 512, v[4], v[5], v[6], v[7]);
  sts128(sb + OFF_GT + row * 64 + x, v[8], v[9], v[10], v[11]);
}
__device__ __forceinline__ void fft_twiddles(float (&v)[4], int tw) {
#pragma unroll
  for (int i = 0; i < 2; i++) {
    float c, s;
    cis((2 * (2 * (tw & 3) + i) - 15) * (4 * (tw >> 2) - 63), 1.f / 4096, c, s);
    v[2 * i] = __fdividef(-s, 1.f + c);
    v[2 * i + 1] = s;
  }
  pin<4>(v);
}
__device__ __forceinline__ void fft_matrices(FftConst& k, uint32_t sb, int w, int lane) {
  const uint32_t x = (lane >> 1) & 3;
  const uint4 t0 = lds128(sb + OFF_TT + 512 * w + 16 * lane), t1 = lds128(sb + OFF_TT + 512 * w + 16 * (lane ^ 3));
  k.ta[0] = __uint_as_float(t0.x); k.tb[0] = __uint_as_float(t0.y); k.ta[1] = __uint_as_float(t0.z); k.tb[1] = __uint_as_float(t0.w);
  k.ta[3] = __uint_as_float(t1.x); k.tb[3] = __uint_as_float(t1.y); k.ta[2] = __uint_as_float(t1.z); k.tb[2] = __uint_as_float(t1.w);
#pragma unroll
  for (int i = 0; i < 2; i++) {
    ldsm4(k.f[i], sb + OFF_FT + (16 * w + (lane & 15)) * 64 + (((2 * i + (lane >> 4)) ^ x) << 4));
    ldsm4t(k.fi[i], sb + OFF_FT + (32 * i + lane) * 64 + ((w ^ x) << 4));
#pragma unroll
    for (int j = 0; j < 4; j++) {
      k.fi[2 + i][j] = (j & 1) ? k.fi[i][j - 1] ^ 0x80008000u : k.fi[i][j + 1];
      asm volatile("" : "+r"(k.fi[2 + i][j]));
    }
  }
}
__device__ __forceinline__ void rot(bool inv, float& x, float& y, float a, float b) {
  x = fmaf(inv ? -a : a, y, x);
  y = fmaf(inv ? -b : b, x, y);
  x = fmaf(inv ? -a : a, y, x);
}
__device__ __forceinline__ void twiddle_fwd(uint32_t (&a)[4][4], float* d, const FftConst& k) {
#pragma unroll
  for (int q = 0; q < 4; q++)
#pragma unroll
    for (int j = 0; j < 2; j++) {
      float* x = d + 8 * q + 4 * j;
      rot(j, x[0], x[2], k.ta[2 * j], k.tb[2 * j]);
      rot(j, x[1], x[3], k.ta[2 * j + 1], k.tb[2 * j + 1]);
      a[q & 2][2 * j + (q & 1)] = pack2(x[0], x[1]);
      a[(q & 2) + 1][2 * j + (q & 1)] = pack2(x[2], x[3]);
    }
}
__device__ __forceinline__ void g_step(float* d, const uint32_t (&a)[4][4], uint32_t dre, uint32_t dim) {
  WgRS<32>::set<HI_SW64>(d, a[0], dre);
  WgRS<32>::set<HI_SW64>(d + 16, a[2], dre);
  WgRS<32>::mma<HI_SW64>(d, a[1], dim);
  WgRS<32>::mma<HI_SW64>(d + 16, a[3], dim);
  wg_commit();
}

__device__ __forceinline__ void conv_channel(const FftConst& k, uint32_t sb, int c, int wg, int w, int lane) {
  const uint32_t cb = sb + off_ch(c), bars = sb + OFF_BAR;
  const uint32_t du = desc_lo(cb, 1024), dg = desc_lo(sb + OFF_GT, 16), dz = desc_lo(cb + U_BYTES, 16);
  float U[32], H[32];
  uint32_t a[4][4], e[4][4];
  const float dv = __uint_as_float(lds32(sb + OFF_D + 4 * c));
  wg_fence();
  WgRS<64>::set<HI_SW32>(H, k.f[0], du + 256);
  WgRS<64>::mma<HI_SW32>(H, k.f[1], du + 256 + 32);
  wg_commit();
  wg_wait<0>();
  pin<32>(H);
  twiddle_fwd(a, H, k);
  if (ATT_GATE && H_EARLY) mbar_wait(bars + 8 * B_ATTN, 0);
  mbar_wait(bars + 8 * (B_U + (c < 3 ? c : 3)), 0);
  TSM(w == 0 && c < 3, 7 + wg);
  wg_fence();
  WgRS<64>::set<HI_SW32>(U, k.f[0], du);
  WgRS<64>::mma<HI_SW32>(U, k.f[1], du + 32);
  wg_commit();
  g_step(H, a, dg, dg + 64);
  wg_wait<1>();
  pin<32>(U);
  twiddle_fwd(e, U, k);
  wg_fence();
  g_step(U, e, dg, dg + 64);
  wg_wait<0>();
  pin<32>(U);
  pin<32>(H);
#pragma unroll
  for (int j = 0; j < 2; j++) {
    float pr[4][2], pi[4][2];
#pragma unroll
    for (int x = 0; x < 2; x++) {
      H[4 * j + x] += dv;
#pragma unroll
      for (int m = 0; m < 4; m++) {
#pragma unroll
        for (int q = 0; q <= m; q++) {
          const int ih = 16 * (q >> 1) + 2 * (q & 1) + 4 * j + x, iu = 16 * ((m - q) >> 1) + 2 * ((m - q) & 1) + 4 * j + x;
          pr[m][x] = q ? fmaf(H[ih], U[iu], pr[m][x]) : H[ih] * U[iu];
          pi[m][x] = q ? fmaf(H[ih], U[iu + 8], pi[m][x]) : H[ih] * U[iu + 8];
          pr[m][x] = fmaf(-H[ih + 8], U[iu + 8], pr[m][x]);
          pi[m][x] = fmaf(H[ih + 8], U[iu], pi[m][x]);
        }
      }
    }
#pragma unroll
    for (int m = 0; m < 4; m++) {
      a[m & 2][2 * j + (m & 1)] = pack2(pr[m][0], pr[m][1]);
      a[(m & 2) + 1][2 * j + (m & 1)] = pack2(pi[m][0], pi[m][1]);
    }
  }
  wg_fence();
  g_step(U, a, dg + 64, dg);
  const uint32_t za = cb + U_BYTES + (8 * w + (lane & 7)) * 128 + (((lane >> 3) ^ (lane & 7)) << 4);
  const uint32_t ya = cb + (lane >> 4) * 1024 + (8 * w + (lane & 7)) * 32 + ((((lane >> 3) ^ (lane >> 2)) & 1) << 4);
  wg_sync(1 + wg);
  wg_wait<0>();
  pin<32>(U);
  TSIF(w == 0, 80 + c);
#pragma unroll
  for (int p = 0; p < 2; p++) {
#pragma unroll
    for (int i = 0; i < 4; i++) {
      const int j = i & 1;
      float* x = U + 16 * p + 4 * j + (i & 2);
      rot(!j, x[8], x[0], k.ta[2 * j], k.tb[2 * j]);
      rot(!j, x[9], x[1], k.ta[2 * j + 1], k.tb[2 * j + 1]);
      e[p][i] = pack2(x[8], x[9]);
      e[2 + p][i] = pack2(x[0], x[1]);
    }
    stsm4(za ^ (64 * p), e[p]);
    stsm4((za ^ (64 * p)) + 4096, e[2 + p]);
  }
  fence_async_smem();
  wg_sync(1 + wg);
  wg_fence();
  WgRS<64>::set<HI_SW128>(H, k.fi[0], dz);
#pragma unroll
  for (int ks = 1; ks < 4; ks++) WgRS<64>::mma<HI_SW128>(H, k.fi[ks], dz + 128 * ks);
  wg_commit();
  wg_wait<0>();
  pin<32>(H);
  TSIF(w == 0, 88 + c);
#pragma unroll
  for (int j = 0; j < 8; j++)
    a[j >> 2][j & 3] = j < 2 ? pack2(H[4 * j], H[4 * j + 1]) : pack2(H[4 * j] + H[4 * j - 6], H[4 * j + 1] + H[4 * j - 5]);
  stsm4(ya, a[0]);
  stsm4(ya + 2048, a[1]);
  fence_async_smem();
  __syncwarp();
}

__device__ __forceinline__ void prep_slab(uint4* res, const uint2* sw, uint32_t sb, int slab, int w, int lane) {
  const int t = lane & 3, tp = (lane & 7) >> 1, pos = 8 * tp + 2 * (((lane >> 3) + tp) & 3) + (lane & 1);
  const uint32_t base = sb + OFF_KVS + slab * KVS_BYTES + pos * 128;
  uint32_t kk[2][4][4], vv[2][4];
#pragma unroll
  for (int h = 0; h < 2; h++) {
#pragma unroll
    for (int j = 0; j < 4; j++) {
      const uint32_t a = base + 128 * j;
      ldsm4t(kk[h][j], a + (((w + 4 * h) ^ ((a >> 7) & 7)) << 4));
    }
    const uint32_t a = base + KVS_V;
    ldsm4t(vv[h], a + (((w + 4 * h) ^ ((a >> 7) & 7)) << 4));
  }
#pragma unroll
  for (int h = 0; h < 2; h++) {
    uint32_t (&k)[4][4] = kk[h];
    uint32_t (&v)[4] = vv[h];
    const uint32_t w0 = __byte_perm(sw[h].x, 0, 0x1010), w1 = __byte_perm(sw[h].x, 0, 0x3232);
    const uint32_t w2 = __byte_perm(sw[h].y, 0, 0x1010), w3 = __byte_perm(sw[h].y, 0, 0x3232);
#pragma unroll
    for (int m = 0; m < 4; m++)
      v[m] = bmul(badd(badd(badd(bmul(k[0][m], w3), bmul(k[1][m], w2)), bmul(k[2][m], w1)), bmul(k[3][m], w0)), v[m]);
    uint32_t a[4];
#pragma unroll
    for (int m = 0; m < 4; m++) a[m] = (t & 1) ? v[(m + 3) & 3] : v[m];
    res[h] = (t & 2) ? make_uint4(a[2], a[3], a[0], a[1]) : make_uint4(a[0], a[1], a[2], a[3]);
  }
}

__device__ __forceinline__ void gate_load(uint32_t (&x)[4], uint32_t sb, uint32_t xa, int kb) {
  mbar_wait(sb + OFF_BAR + 8 * (B_FULL1 + (kb & 3)), (kb >> 2) & 1);
#pragma unroll
  for (int i = 0; i < 4; i++) x[i] = lds32((xa ^ (144 * (i >> 1))) + (i & 1) * 8192 + (kb & 3) * STAGE_BYTES);
}
__device__ __forceinline__ void gate_add(float (&z)[4], uint32_t (&gw)[10], const uint32_t (&x)[4], uint32_t sb, int kb, int lane, uint32_t zero) {
  if (lane == 0) mbar_arrive(sb + OFF_BAR + 8 * (kb == 3 ? B_E3 : kb == 9 ? B_P1 : B_EMPTY1 + (kb & 3)) + ((x[0] ^ x[1] ^ x[2] ^ x[3]) & zero));
#pragma unroll
  for (int i = 0; i < 4; i++) {
    const uint32_t m = bmul(x[i], gw[0]);
    z[i] += bf_lo(m) + bf_hi(m);
  }
#pragma unroll
  for (int i = 0; i < 9; i++) gw[i] = gw[i + 1];
}
__device__ __forceinline__ void gate_step(float (&z)[4], uint32_t (&gw)[10], uint32_t sb, uint32_t xa, int kb, int lane, uint32_t zero) {
  uint32_t x[4];
  gate_load(x, sb, xa, kb);
  gate_add(z, gw, x, sb, kb, lane, zero);
}

__device__ __forceinline__ uint32_t bmax(uint32_t a, uint32_t b) {
  uint32_t d;
  asm("max.bf16x2 %0, %1, %2;" : "=r"(d) : "r"(a), "r"(b));
  return d;
}
__device__ __forceinline__ void softmax_two(const float (&l)[2][2], uint32_t& p0, uint32_t& p1) {
  constexpr float kScale = 0.22360679774997896f, kLog2e = 1.4426950408889634f;
  const uint32_t r0 = pack2(l[0][0], l[1][0]), r1 = pack2(l[0][1], l[1][1]);
  const uint32_t x0 = pack2(bf_lo(r0) * kScale, bf_hi(r0) * kScale), x1 = pack2(bf_lo(r1) * kScale, bf_hi(r1) * kScale);
  uint32_t m = bmax(x0, x1);
  m = bmax(m, __shfl_xor_sync(0xffffffffu, m, 1));
  m = bmax(m, __shfl_xor_sync(0xffffffffu, m, 2));
  const float m0 = bf_lo(m) * kLog2e, m1 = bf_hi(m) * kLog2e;
  p0 = pack2(ex2(bf_lo(x0) * kLog2e - m0), ex2(bf_lo(x1) * kLog2e - m0));
  p1 = pack2(ex2(bf_hi(x0) * kLog2e - m1), ex2(bf_hi(x1) * kLog2e - m1));
}

__device__ __forceinline__ void halo_read(uint32_t (&kpv)[10], uint32_t (&vpv)[10], uint32_t (&tg)[7], const uint4* hp) {
#pragma unroll
  for (int j = 0; j < 7; j++) {
    uint32_t x0, x1, x2;
    asm volatile("ld.relaxed.gpu.global.v4.u32 {%0, %1, %2, %3}, [%4];"
                 : "=r"(x0), "=r"(x1), "=r"(x2), "=r"(tg[j]) : "l"(hp + 32 * j) : "memory");
    if (j < 4) kpv[3 * j] = x0; else vpv[3 * j - 10] = x0;
    if (j < 3) kpv[3 * j + 1] = x1; else vpv[3 * j - 9] = x1;
    if (j < 3) kpv[3 * j + 2] = x2; else if (j < 6) vpv[3 * j - 8] = x2;
  }
}

template <int ROT>
__device__ __forceinline__ void pack_qkv(const float* acc, uint32_t (&qlo)[10], uint32_t (&qhi)[10], uint32_t (&klo)[10],
                                         uint32_t (&khi)[10], uint32_t (&vlo)[10], uint32_t (&vhi)[10]) {
#pragma unroll
  for (int j = 0; j < 10; j++) {
    const int x = (j + ROT) % 10, tq = x < 8 ? x : 16 + x, tk = x < 8 ? 8 + x : 18 + x, tv = x < 8 ? 16 + x : 20 + x;
    khi[j] = pack2(acc[4 * tk + 2], acc[4 * tk + 3]);
    vhi[j] = movm(pack2(acc[4 * tv + 2], acc[4 * tv + 3]));
    qlo[j] = pack2(acc[4 * tq], acc[4 * tq + 1]);
    qhi[j] = pack2(acc[4 * tq + 2], acc[4 * tq + 3]);
    klo[j] = pack2(acc[4 * tk], acc[4 * tk + 1]);
    vlo[j] = pack2(acc[4 * tv], acc[4 * tv + 1]);
    asm volatile("" : "+r"(khi[j]), "+r"(qlo[j]), "+r"(qhi[j]), "+r"(klo[j]), "+r"(vlo[j]));
  }
}

template <int ROT> __device__ __forceinline__ void halo_send(const float* acc, uint4* ho, uint32_t tag) {
#pragma unroll
  for (int j = 0; j < 7; j++) {
    uint32_t x[3];
#pragma unroll
    for (int e = 0; e < 3; e++) {
      const int i = 3 * j + e, y = (i % 10 + ROT) % 10, tk = y < 8 ? 8 + y : 18 + y, tv = y < 8 ? 16 + y : 20 + y;
      x[e] = i < 10 ? pack2(acc[4 * tk + 2], acc[4 * tk + 3]) : i < 20 ? movm(pack2(acc[4 * tv + 2], acc[4 * tv + 3])) : 0u;
    }
    asm volatile("st.relaxed.gpu.global.v4.u32 [%0], {%1, %2, %3, %4};" ::"l"(ho + 32 * j), "r"(x[0]), "r"(x[1]), "r"(x[2]), "r"(tag) : "memory");
  }
}

__device__ __forceinline__ void attention(float* acc, uint32_t sb, int b, int par, int w, int lane, uint32_t tag) {
  const int g = lane >> 2, t = lane & 3;
  uint32_t klo[10], khi[10], vlo[10], vhi[10], qlo[10], qhi[10], kpv[10], vpv[10];
  if (HALO_FIRST && w == 3 && b < NCTA - 8) {
    uint4* ho = g_halo + (b * 2 + par) * 224 + lane;
    if (tail_first(b & 7)) halo_send<8>(acc, ho, tag);
    else halo_send<0>(acc, ho, tag);
    TSIF(par == 0, 76);
    pin<120>(acc);
  }
  if (tail_first(b & 7)) pack_qkv<8>(acc, qlo, qhi, klo, khi, vlo, vhi);
  else pack_qkv<0>(acc, qlo, qhi, klo, khi, vlo, vhi);
  const uint32_t xa = sb + OFF_KVX + (par * 3) * 2560 + lane * 16;
  if (w < 3) {
    sts128(xa + w * 2560, khi[0], khi[1], khi[2], khi[3]);
    sts128(xa + w * 2560 + 512, khi[4], khi[5], khi[6], khi[7]);
    sts128(xa + w * 2560 + 1024, khi[8], khi[9], vhi[0], vhi[1]);
    sts128(xa + w * 2560 + 1536, vhi[2], vhi[3], vhi[4], vhi[5]);
    sts128(xa + w * 2560 + 2048, vhi[6], vhi[7], vhi[8], vhi[9]);
  } else if (!HALO_FIRST && b < NCTA - 8) {
    uint4* ho = g_halo + (b * 2 + par) * 224 + lane;
#pragma unroll
    for (int j = 0; j < 7; j++) {
      const uint32_t x0 = j < 4 ? khi[3 * j] : vhi[3 * j - 10], x1 = j < 3 ? khi[3 * j + 1] : vhi[3 * j - 9];
      const uint32_t x2 = j < 3 ? khi[3 * j + 2] : j < 6 ? vhi[3 * j - 8] : 0u;
      asm volatile("st.relaxed.gpu.global.v4.u32 [%0], {%1, %2, %3, %4};" ::"l"(ho + 32 * j), "r"(x0), "r"(x1), "r"(x2), "r"(tag) : "memory");
    }
  }
  TSIF(par == 0 && w == 1, 64);
  TSIF(par == 0 && w == 3 && !HALO_FIRST, 76);
#pragma unroll
  for (int j = 0; j < 10; j++) vlo[j] = movm(vlo[j]);
  const bool far0 = 2 * t > g, far1 = 2 * t + 1 > g;
  const uint32_t mfar = (far0 ? 0x0000FFFFu : 0u) | (far1 ? 0xFFFF0000u : 0u);
  float slo[4][2], shi[4][2], lg[2][2];
  uint32_t phi[4], plo[4], qml[4], qmh[4];
#pragma unroll
  for (int h = 0; h < 4; h++) {
    const int f = h == 0 ? 0 : h == 1 ? 3 : h == 2 ? 5 : 8, hf = h < 2 ? 2 : 7;
    const bool mine = (h & 1) ? t >= 2 : t < 2;
    qml[h] = mine ? qlo[hf] : 0u;
    qmh[h] = mine ? qhi[hf] : 0u;
    float a[4] = {0.f, 0.f, 0.f, 0.f}, c[4] = {0.f, 0.f, 0.f, 0.f};
    mma16816(a, qlo[f], qhi[f], qlo[f + 1], qhi[f + 1], klo[f], klo[f + 1]);
    mma16816(c, qlo[f], qhi[f], qlo[f + 1], qhi[f + 1], khi[f], khi[f + 1]);
    mma1688(a, qml[h], qmh[h], klo[hf]);
    mma1688(c, qml[h], qmh[h], khi[hf]);
    slo[h][0] = a[0];
    slo[h][1] = a[1];
    shi[h][0] = lg[h & 1][0] = far0 ? a[2] : c[2];
    shi[h][1] = lg[h & 1][1] = far1 ? a[3] : c[3];
    if (!ATT_MERGE && (h & 1)) softmax_two(lg, phi[h - 1], phi[h]);
  }
  TSIF(par == 0 && w == 1, 65);
  wg_sync(1 + par);
  TSIF(par == 0 && w == 1, 66);
  const bool nohist = (w == 0) && (b < 8);
  const uint4* hp = g_halo + ((b - 8) * 2 + par) * 224 + lane;
  uint32_t tg[7];
  if (w > 0) {
    const uint4 v0 = lds128(xa + (w - 1) * 2560), v1 = lds128(xa + (w - 1) * 2560 + 512), v2 = lds128(xa + (w - 1) * 2560 + 1024);
    const uint4 v3 = lds128(xa + (w - 1) * 2560 + 1536), v4 = lds128(xa + (w - 1) * 2560 + 2048);
    kpv[0] = v0.x; kpv[1] = v0.y; kpv[2] = v0.z; kpv[3] = v0.w; kpv[4] = v1.x; kpv[5] = v1.y; kpv[6] = v1.z; kpv[7] = v1.w;
    kpv[8] = v2.x; kpv[9] = v2.y; vpv[0] = v2.z; vpv[1] = v2.w; vpv[2] = v3.x; vpv[3] = v3.y; vpv[4] = v3.z; vpv[5] = v3.w;
    vpv[6] = v4.x; vpv[7] = v4.y; vpv[8] = v4.z; vpv[9] = v4.w;
  } else if (nohist) {
#pragma unroll
    for (int j = 0; j < 10; j++) kpv[j] = vpv[j] = 0u;
  } else {
    TSIF(par == 0, 77);
    halo_read(kpv, vpv, tg, hp);
  }
  if (w == 0 && !nohist) {
    int spins = 0;
    while (true) {
      bool ok = true;
#pragma unroll
      for (int j = 0; j < 7; j++) ok = ok && tg[j] == tag;
      if (__all_sync(0xffffffffu, ok) || ++spins > SPIN_LIMIT) break;
      halo_read(kpv, vpv, tg, hp);
    }
    TSIF(par == 0, 79);
  }
#pragma unroll
  for (int h = 0; h < 4; h++) {
    const int f = h == 0 ? 0 : h == 1 ? 3 : h == 2 ? 5 : 8, hf = h < 2 ? 2 : 7;
    float a[4] = {0.f, 0.f, 0.f, 0.f};
    mma16816(a, qlo[f], qhi[f], qlo[f + 1], qhi[f + 1], kpv[f], kpv[f + 1]);
    mma1688(a, qml[h], qmh[h], kpv[hf]);
    const float ninf = __int_as_float(0xff800000);
    lg[h & 1][0] = far0 ? (nohist ? ninf : a[0]) : slo[h][0];
    lg[h & 1][1] = far1 ? (nohist ? ninf : a[1]) : slo[h][1];
    if (h & 1) {
      softmax_two(lg, plo[h - 1], plo[h]);
      if (ATT_MERGE) {
        const float lh[2][2] = {{shi[h - 1][0], shi[h - 1][1]}, {shi[h][0], shi[h][1]}};
        softmax_two(lh, phi[h - 1], phi[h]);
      }
    }
  }
  TSIF(par == 0 && w <= 1, 67 + w);
  uint32_t ov[20];
#pragma unroll
  for (int hp = 0; hp < 2; hp++) {
    const int hf = hp ? 7 : 2;
    float sh[4] = {0.f, 0.f, 0.f, 0.f}, i0 = 0.f, i1 = 0.f;
#pragma unroll
    for (int e = 0; e < 2; e++) {
      const int h = 2 * hp + e, f = h == 0 ? 0 : h == 1 ? 3 : h == 2 ? 5 : 8;
      const uint32_t a0 = plo[h] & mfar, a2 = plo[h] & ~mfar, a3 = phi[h] & mfar, c1 = phi[h] & ~mfar;
      float sum[4] = {0.f, 0.f, 0.f, 0.f};
      mma1688(sum, plo[h], phi[h], 0x3F803F80u);
      const float r0 = rcp(sum[0]), r1 = rcp(sum[2]);
#pragma unroll
      for (int j = f; j < f + 2; j++) {
        float o[4] = {0.f, 0.f, 0.f, 0.f};
        mma16816(o, a0, 0u, a2, a3, vpv[j], vlo[j]);
        mma1688(o, 0u, c1, vhi[j]);
        ov[2 * j] = pack2(o[0] * r0, o[1] * r0);
        ov[2 * j + 1] = pack2(o[2] * r1, o[3] * r1);
      }
      const bool mine = e ? g >= 4 : g < 4;
      mma16816(sh, a0, 0u, a2, a3, mine ? vpv[hf] : 0u, mine ? vlo[hf] : 0u);
      mma1688(sh, 0u, c1, mine ? vhi[hf] : 0u);
      if (e == 0 || t >= 2) {
        i0 = r0;
        i1 = r1;
      }
    }
    ov[2 * hf] = pack2(sh[0] * i0, sh[1] * i0);
    ov[2 * hf + 1] = pack2(sh[2] * i1, sh[3] * i1);
  }
  TS(32 + 4 * par + w);
  mbar_wait(sb + OFF_BAR + 8 * B_P1, 0);
  const uint32_t oa = sb + OFF_OA + (lane >> 4) * 2048 + (32 * w + 2 * (lane & 15) + par) * 16;
#pragma unroll
  for (int j = 0; j < 5; j++) stsm4(oa + 4096 * j, ov + 4 * j);
  TSIF(par == 0 && w == 0, 120);
  fence_async_smem();
  TSIF(par == 0 && w == 0, 121);
  __syncwarp();
  if (lane == 0) mbar_arrive(sb + OFF_BAR + 8 * B_ATTN);
  TSM(w == 0 || w == 2, 122 + par + (w == 2 ? 3 : 0));
}

struct Maps {
  CUtensorMap x, wm, wt, k, v, y, wo, qm, qt, om, ot, u;
};

__device__ __forceinline__ void load_stage(uint32_t sb, int kb, int b, const Maps& m) {
  const uint32_t st = sb + (kb & 3) * STAGE_BYTES, bar = sb + OFF_BAR + 8 * (B_FULL1 + (kb & 3));
  const int r = b >> 3, hg = b & 7, slab = kb - KV_KB;
  const bool kv = slab >= 0 && slab < 5;
  const uint32_t kbar = sb + OFF_BAR + 8 * (B_KV + slab), dst = sb + OFF_KVS + slab * KVS_BYTES;
  mbar_expect_tx(bar, STAGE_BYTES);
  if (kv) mbar_expect_tx(kbar, KVS_BYTES);
  tma_3d(st, &m.x, 64 * kb, 64 * r, 0, bar);
  if (kv && KV_MIX) tma_3d(dst, &m.k, 0, 32 * (b >> 1) - 3, 2 * slab + (b & 1), kbar);
  tma_3d(st + ST_W, &m.wm, 80 * hg + (tail_first(hg) ? 16 : 0), 64 * kb, 0, bar);
  if (kv && KV_MIX) tma_3d(dst + KVS_V, &m.v, 0, 32 * (b >> 1), 2 * slab + (b & 1), kbar);
  tma_3d(st + ST_WT, &m.wt, 80 * hg + (tail_first(hg) ? 0 : 64), 64 * kb, 0, bar);
  if (kv && !KV_MIX) tma_3d(dst, &m.k, 0, 32 * (b >> 1) - 3, 2 * slab + (b & 1), kbar);
  if (kv && !KV_MIX) tma_3d(dst + KVS_V, &m.v, 0, 32 * (b >> 1), 2 * slab + (b & 1), kbar);
}

__global__ void __launch_bounds__(NTHR, 1) fused_kernel(const __grid_constant__ Maps m, const Params p) {
  extern __shared__ __align__(1024) uint8_t smem[];
  const uint32_t sb = (uint32_t)__cvta_generic_to_shared(smem);
  const uint32_t bars = sb + OFF_BAR;
  const int tid = threadIdx.x, lane = tid & 31;
  int b = blockIdx.x;
  if (BMAP == 1) b = (((b & 63) >> 3) * 2 + (b & 1)) * 8 + (((b < 64 ? 0x6521 : 0x7430) >> (4 * ((b >> 1) & 3))) & 7);
  if (BMAP == 2) b = ((b & 63) >> 2) * 8 + (((b < 64 ? 0x6521 : 0x7430) >> (4 * (b & 3))) & 7);
  if (BMAP == 3) b = (((b & 63) >> 3) * 2 + (b & 1)) * 8 + (((b < 64 ? 0x7430 : 0x6521) >> (4 * ((b >> 1) & 3))) & 7);
  if (BMAP == 4) b = (((b >> 4) * 2 + (b & 1)) * 8) + ((b >> 1) & 7);
  if (BMAP == 5) b = 127 - b;
  const int r = b >> 3, hg = b & 7;

  if (tid == T_ISSUE) {
    TSM(true, 0);
#pragma unroll
    for (int i = 0; i < 4; i++) mbar_init(bars + 8 * (B_FULL1 + i), 1);
#pragma unroll
    for (int i = 0; i < 3; i++) mbar_init(bars + 8 * (B_KV + i), 1);
    fence_async_smem();
#pragma unroll 1
    for (int kb = 0; kb <= PRE2; kb++) load_stage(sb, kb, b, m);
  } else if (tid >= T_PF && tid < T_PF + 12) {
    tm_prefetch(&m.x + (tid - T_PF));
  } else if (tid == T_INIT) {
#pragma unroll
    for (int i = 0; i < 4; i++) mbar_init(bars + 8 * (B_EMPTY1 + i), 12);
#pragma unroll
    for (int i = 0; i < 8; i++) mbar_init(bars + 8 * (B_FULL2 + i), 1);
#pragma unroll
    for (int i = 0; i < 4; i++) mbar_init(bars + 8 * (B_EMPTY2 + i), 8);
#pragma unroll
    for (int i = 0; i < 4; i++) mbar_init(bars + 8 * (B_U + i), 1);
    mbar_init(bars + 8 * B_HA, 4);
    mbar_init(bars + 8 * B_GATE, 4);
    mbar_init(bars + 8 * B_HB, 1);
    mbar_init(bars + 8 * B_KVD, 4);
    mbar_init(bars + 8 * B_QF, 1);
    mbar_init(bars + 8 * B_ATTN, 8);
    mbar_init(bars + 8 * B_P1, 12);
    mbar_init(bars + 8 * B_C34, 1);
#pragma unroll
    for (int i = 0; i < 5; i++) mbar_init(bars + 8 * (B_YST + i), 4);
#pragma unroll
    for (int i = 0; i < 5; i++) mbar_init(bars + 8 * (B_US + i), 4);
    mbar_init(bars + 8 * B_YSIG, 1);
    mbar_init(bars + 8 * B_YFULL, 1);
    mbar_init(bars + 8 * B_EPOCH, 1);
    mbar_init(bars + 8 * B_PREP, 4);
    mbar_init(bars + 8 * B_USIG, 1);
    mbar_init(bars + 8 * B_WST, 1);
#pragma unroll
    for (int i = 3; i < 5; i++) mbar_init(bars + 8 * (B_KV + i), 1);
    mbar_init(bars + 8 * B_E3, 12);
    mbar_init(bars + 8 * B_LAST, 1);
    mbar_init(bars + 8 * B_OSIG, 1);
    mbar_init(bars + 8 * B_WOP, 1);
    fence_async_smem();
  }
  const int warp = __shfl_sync(0xffffffffu, tid >> 5, 0), wg = warp >> 2, w = warp & 3;
  __syncthreads();

  if (wg == 3) {
    asm volatile("setmaxnreg.dec.sync.aligned.u32 56;");
    if (w == 0) {
      if (lane == 0) {
#pragma unroll 1
        for (int kb = 1 + PRE2; kb < 10; kb++) {
          if (kb >= 4) mbar_wait(bars + 8 * (kb == 7 ? B_E3 : B_EMPTY1 + (kb & 3)), (kb >> 3) & 1);
          TSIF(kb >= 4, 44 + kb);
          load_stage(sb, kb, b, m);
          TSIF(kb == 3, 60);
          if (kb == TRIG_KB) mbar_arrive(bars + 8 * B_LAST);
        }
        mbar_wait(bars + 8 * B_WOP, 0);
        mbar_wait(bars + 8 * WL_TRIG, 0);
        mbar_wait(bars + 8 * B_EPOCH, 0);
        flag_wait(g_cnt + C_W + 32 * hg, (lds32(sb + OFF_EPOCH) + 1) * 16);
        TS(30);
#pragma unroll 1
        for (int j = 0; j < 8; j++) {
          if (j >= 6) mbar_wait(bars + 8 * (B_EMPTY2 + j - 6), 0);
          if (j == 4) mbar_wait(bars + 8 * B_ATTN, 0);
          TSIF(j >= 6, 100 + j);
          if (RF_GATE && j == 6) mbar_wait(bars + 8 * B_YSIG, 0);
          mbar_expect_tx(bars + 8 * (B_FULL2 + j), j == 0 ? WO_BYTES : j == 5 ? O_BYTES + WO_BYTES + 512 : O_BYTES + WO_BYTES);
          bulk_load(sb + off_w(j), g_WO + (hg * 8 + step_src(hg, j)) * 800, WO_BYTES, bars + 8 * (B_FULL2 + j));
        }
        mbar_wait(bars + 8 * (B_EMPTY2 + 3), 0);
        mbar_expect_tx(bars + 8 * B_QF, O_BYTES);
        tma_2d(sb + OFF_QS, &m.qm, 80 * hg, 128 * r, bars + 8 * B_QF);
        tma_2d(sb + OFF_QT, &m.qt, 80 * hg + 64, 128 * r, bars + 8 * B_QF);
      }
    } else if (w == 1) {
      unsigned epoch = 0;
      if (lane == 0) {
        epoch = atomicAdd(g_cnt + C_LAUNCH, 1u) / NCTA;
        asm volatile("st.shared.u32 [%0], %1;" ::"r"(sb + OFF_EPOCH), "r"(epoch) : "memory");
        mbar_arrive(bars + 8 * B_EPOCH);
        mbar_wait(bars + 8 * B_KVD, 0);
        mbar_expect_tx(bars + 8 * B_HB, 5 * 4096);
#pragma unroll 1
        for (int c = 0; c < 5; c++) {
          if (c == 3) mbar_wait(bars + 8 * B_S3, 0);
          bulk_load(sb + off_ch(c) + U_BYTES, p.ssm_k + (5 * b + c) * SEQ, 4096, bars + 8 * B_HB);
        }
#pragma unroll
        for (int c = 0; c < 4; c++) mbar_expect_tx(bars + 8 * (B_U + c), c < 3 ? U_BYTES : 2 * U_BYTES);
        const uint4* usrc = g_U + 5 * b * U_PITCH;
        mbar_wait(bars + 8 * B_USIG, 0);
        flag_wait(g_cnt + C_PREP + 32 * (b & 15), (epoch + 1) * NCTA);
        TS(23);
#pragma unroll
        for (int c = 0; c < 5; c++) {
          if (c == 3) mbar_wait(bars + 8 * (B_U + 2), 0);
          bulk_load(sb + off_ch(c), usrc + c * U_PITCH, U_BYTES, bars + 8 * (B_U + (c < 3 ? c : 3)));
          TSIF(c == 0 || c == 4, 116 + (c >> 2));
        }
      }
      epoch = __shfl_sync(0xffffffffu, epoch, 0);
      if (lane < 8) {
        const int src = (b & ~7) | step_src(hg, lane);
        mbar_wait(bars + 8 * B_OSIG, 0);
        TS(20);
        flag_wait(g_cnt + C_O + 32 * src, epoch + 1);
        if (lane >= 1 && lane < 4) bulk_load(sb + off_o(lane), g_O + src * 1280, O_BYTES, bars + 8 * (B_FULL2 + lane));
        __syncwarp(0xff);
        TS(21);
        if (lane == 5) bulk_load(sb + OFF_GATE, g_gate + 128 * r, 512, bars + 8 * (B_FULL2 + 5));
#pragma unroll 1
        for (int j = 4; j < 8; j++) {
          if (lane == j) {
            mbar_wait(bars + 8 * (j < 6 ? B_C34 : B_EMPTY2 + j - 6), 0);
            if (RF_GATE && j == 6) mbar_wait(bars + 8 * B_YSIG, 0);
            bulk_load(sb + off_o(j), g_O + src * 1280, O_BYTES, bars + 8 * (B_FULL2 + j));
          }
          __syncwarp(0xff);
        }
        TS(22);
      }
    } else if (w == 2) {
      mbar_wait(bars + 8 * B_PREP, 0);
      flag_signal(g_cnt + C_PREP, 16, lane);
      TS(25);
      if (lane == 0) mbar_arrive(bars + 8 * B_USIG);
      mbar_wait(bars + 8 * B_GATE, 0);
      if ((NOMB & 1) && lane == 0) asm volatile("fence.release.gpu;" ::: "memory");
      mbar_wait(bars + 8 * B_ATTN, 0);
      if (lane == 0) {
        if (O_DEFER) mbar_wait(bars + 8 * (B_U + 3), 0);
        asm volatile("cp.async.bulk.global.shared::cta.bulk_group [%0], [%1], 20480;\ncp.async.bulk.commit_group;\n"
                     "cp.async.bulk.wait_group 0;\nfence.proxy.async.global;" ::"l"(g_O + b * 1280), "r"(sb + OFF_OA) : "memory");
      }
      TS(74);
      if (!(NOMB & 1)) flag_signal(g_cnt + C_O + 32 * b, 1, lane);
      else if (lane == 0) flag_bump(g_cnt + C_O + 32 * b);
      TS(26);
      if (lane == 0) mbar_arrive(bars + 8 * B_OSIG);

    } else {
      if (lane == 0) {
        uint4* dst = g_WO + (hg * 8 + (r >> 1)) * 800 + (r & 1) * 80;
        mbar_wait(bars + 8 * B_P1, 0);
        mbar_wait(bars + 8 * WB_TRIG, 0);
        mbar_expect_tx(bars + 8 * B_WST, WO_BYTES / 2);
        tma_3d(sb + OFF_WS, &m.wo, 0, 40 * r, 5 * hg, bars + 8 * B_WST);
        mbar_wait(bars + 8 * B_WST, 0);
        mbar_wait(bars + 8 * WO_TRIG, 0);
#pragma unroll 1
        for (int n = 0; n < 5; n++)
          asm volatile("cp.async.bulk.global.shared::cta.bulk_group [%0], [%1], 1280;" ::"l"(dst + 160 * n), "r"(sb + OFF_WS + 1280 * n) : "memory");
        asm volatile("cp.async.bulk.commit_group;\ncp.async.bulk.wait_group 0;\nfence.proxy.async.global;" ::: "memory");
        if (!(NOMB & 4)) asm volatile("fence.release.gpu;" ::: "memory");
        flag_bump(g_cnt + C_W + 32 * hg);
        mbar_arrive(bars + 8 * B_WOP);
        TS(71);
#pragma unroll 1
        for (int c = 0; c < 5; c++) {
          mbar_wait(bars + 8 * (B_YST + c), 0);
          asm volatile("cp.async.bulk.global.shared::cta.bulk_group [%0], [%1], 4096;\ncp.async.bulk.commit_group;"
                       ::"l"(g_Y + (5 * b + c) * Y_PITCH), "r"(sb + off_ch(c)) : "memory");
          if (c == 2) {
            asm volatile("cp.async.bulk.wait_group.read 0;" ::: "memory");
            mbar_arrive(bars + 8 * B_C34);
          }
        }
        asm volatile("cp.async.bulk.wait_group 0;\nfence.proxy.async.global;" ::: "memory");
        TS(75);
        if (!(NOMB & 2)) asm volatile("fence.release.gpu;" ::: "memory");
        flag_bump(g_cnt + C_Y + 32 * (b >> 4));
        TS(27);
        mbar_arrive(bars + 8 * B_YSIG);
        mbar_expect_tx(bars + 8 * B_YFULL, 20480);
        flag_wait(g_cnt + C_Y + 32 * hg, (lds32(sb + OFF_EPOCH) + 1) * 16);
        TS(24);
        tma_2d(sb + OFF_YT, &m.y, 128 * r, 80 * hg, bars + 8 * B_YFULL);
        tma_2d(sb + OFF_YT + 10240, &m.y, 128 * r + 64, 80 * hg, bars + 8 * B_YFULL);
      }
    }
  } else {
    asm volatile("setmaxnreg.inc.sync.aligned.u32 152;");
    if (wg < 2) {
      float acc[120];
#pragma unroll
      for (int i = 0; i < 120; i++) acc[i] = 0.f;
      const uint32_t da = desc_lo(sb + wg * 8192, 16), db = desc_lo(sb + ST_W, 8192), dc = desc_lo(sb + ST_WT, 2048);
      if (PW1) pin<120>(acc);
      if (PW1 == 2) mbar_wait(bars + 8 * B_FULL1, 0);
#pragma unroll 1
      for (int kb = 0; kb < 10; kb++) {
        mbar_wait(bars + 8 * (B_FULL1 + (kb & 3)), (kb >> 2) & 1);
        const uint32_t so = (kb & 3) * (STAGE_BYTES >> 4);
        wg_fence();
#pragma unroll
        for (int k = 0; k < 4; k++) {
          WgSST<192>::mma<HI_SW128, HI_SW128>(acc, da + so + 2 * k, db + so + 128 * k, 1);
          WgSST<48>::mma<HI_SW128, HI_SW32>(acc + 96, da + so + 2 * k, dc + so + 32 * k, 1);
        }
        wg_commit();
        wg_wait<1>();
        if (kb > 0 && lane == 0) mbar_arrive(bars + 8 * (kb == 4 ? B_E3 : B_EMPTY1 + ((kb - 1) & 3)));
      }
      mbar_wait(bars + 8 * B_EPOCH, 0);
      const uint32_t tag = lds32(sb + OFF_EPOCH) + 1;
      mbar_wait(bars + 8 * B_S3, 0);
      wg_wait<0>();
      pin<120>(acc);
      if (lane == 0) mbar_arrive(bars + 8 * B_P1);
      TSM(w == 0, 3 + wg);
      attention(acc, sb, b, wg, w, lane, tag);
    } else {
      const int tw = tid & 127, chl = 64 * (b & 1) + 8 * w + (lane >> 2);
      uint4* up = g_U + chl * U_PITCH + ((4 * (b >> 1) + (lane & 3)) ^ ((b >> 2) & 1));
      uint2 sw[10];
      uint32_t dv = 0;
      if (lane < 5) dv = __ldg(reinterpret_cast<const unsigned short*>(p.ssm_D) + 5 * b + lane);
#pragma unroll
      for (int i = 0; i < 10; i++) sw[i] = ldg64(reinterpret_cast<const uint2*>(p.shift_k) + chl + 128 * (i >> 1) + 32 * (i & 1));
      uint32_t gw[10];
#pragma unroll
      for (int i = 0; i < 10; i++) gw[i] = __ldg(reinterpret_cast<const uint32_t*>(p.gate_w) + 32 * i + lane);
      uint32_t tab[12];
      float tt[4];
      fft_tables(tab, tw);
      fft_twiddles(tt, tw);
      uint4 res[10];
#pragma unroll
      for (int i = 0; i < 10; i++) res[i] = make_uint4(0, 0, 0, 0);
      const uint32_t xa = sb + (8 * hg + 2 * w) * 128 + (((lane >> 2) ^ (2 * w)) << 4) + 4 * (lane & 3);
      float z[4] = {0.f, 0.f, 0.f, 0.f};
#pragma unroll 1
      for (int kb = 0; kb < KV_KB + G_LAG; kb++) gate_step(z, gw, sb, xa, kb, lane, p.zero);
#pragma unroll 1
      for (int slab = 0; slab < 5; slab++) {
        uint32_t x[4];
        mbar_wait(bars + 8 * (B_KV + slab), 0);
        gate_load(x, sb, xa, slab + KV_KB + G_LAG);
#pragma unroll
        for (int i = 0; i < 8; i++) res[i] = res[i + 2];
        prep_slab(res + 8, sw, sb, slab, w, lane);
        gate_add(z, gw, x, sb, slab + KV_KB + G_LAG, lane, p.zero);
        TSIF(w == 0, 99 + 4 * slab);
#pragma unroll
        for (int i = 0; i < 8; i++) sw[i] = sw[i + 2];
      }
      TSIF(w == 0, 28);
      __syncwarp();
      if (lane == 0) mbar_arrive(bars + 8 * B_KVD + ((res[8].x ^ res[9].x) & p.zero));
#pragma unroll 1
      for (int kb = KV_KB + G_LAG + 5; kb < 8; kb++) gate_step(z, gw, sb, xa, kb, lane, p.zero);
      mbar_wait(bars + 8 * B_KVD, 0);
      fft_tables_store(tab, sb, tw);
      mbar_wait(bars + 8 * B_LAST, 0);
#pragma unroll
      for (int i = 0; i < 10; i++) up[(128 * (i >> 1) + 32 * (i & 1)) * U_PITCH] = res[i];
      __syncwarp();
      if (lane == 0) mbar_arrive(bars + 8 * B_PREP);
      TSIF(w == 0 && !U_TMA, 5);
#pragma unroll 1
      for (int kb = 8; kb < 10; kb++) gate_step(z, gw, sb, xa, kb, lane, p.zero);
      {
        const bool h = lane & 16, q = lane & 8;
        const float a = (h ? z[2] : z[0]) + __shfl_xor_sync(0xffffffffu, h ? z[0] : z[2], 16);
        const float c = (h ? z[3] : z[1]) + __shfl_xor_sync(0xffffffffu, h ? z[1] : z[3], 16);
        float y = (q ? c : a) + __shfl_xor_sync(0xffffffffu, q ? a : c, 8);
#pragma unroll
        for (int o = 4; o > 0; o >>= 1) y += __shfl_xor_sync(0xffffffffu, y, o);
        y = bf_lo(pack2(y, 0.f));
        if ((lane & 7) == 0) g_gate[16 * b + (tw >> 3)] = bf_lo(pack2(__fdividef(1.f, 1.f + __expf(-y)), 0.f));
      }
      __syncwarp();
      if (lane == 0) mbar_arrive(bars + 8 * B_GATE);
      TSIF(w == 0, 72);
      mbar_wait(bars + 8 * B_HB, 0);
      TSIF(w == 0, 2);
      const uint32_t ha = sb + U_BYTES + ((tw >> 3) * 16 + 8 + (tw & 7)) * 16;
      uint4 hv[5];
#pragma unroll
      for (int c = 0; c < 5; c++) hv[c] = lds128(ha + off_ch(c));
      __syncwarp();
#pragma unroll
      for (int c = 0; c < 5; c++) sts128((ha ^ 16) + off_ch(c), hv[c].x, hv[c].y, hv[c].z, hv[c].w);
      sts128(sb + OFF_TT + 16 * tw, __float_as_uint(tt[0]), __float_as_uint(tt[1]), __float_as_uint(tt[2]), __float_as_uint(tt[3]));
      if (tw < 5) asm volatile("st.shared.f32 [%0], %1;" ::"r"(sb + OFF_D + 4 * tw), "f"(bf_lo(dv) * 0.125f) : "memory");
      fence_async_smem();
      __syncwarp();
      if (lane == 0) mbar_arrive(bars + 8 * B_HA);
      TSIF(w == 0, 6);
    }

    FftConst fc;
    TSM(w == 0 && wg == 0, 104);
    mbar_wait(bars + 8 * B_HA, 0);
    fft_matrices(fc, sb, w, lane);
    TSM(w == 0 && wg == 0, 105);
    if (ATT_GATE && !H_EARLY) mbar_wait(bars + 8 * B_ATTN, 0);
    TSM(w == 0 && wg == 2, 124);
#pragma unroll 1
    for (uint32_t tasks = wg == 0 ? TASK0 : wg == 1 ? TASK1 : TASK2; tasks; tasks >>= 4) {
      const int c = (tasks & 7) - 1;
      conv_channel(fc, sb, c, wg, w, lane);
      if (lane == 0) mbar_arrive(bars + 8 * (B_YST + c));
      TSM(w == 0, 10 + c);
    }

    if (wg < 2) {
      const int g = lane >> 2;
      float acc[40];
#pragma unroll
      for (int i = 0; i < 40; i++) acc[i] = 0.f;
      const uint32_t da = desc_lo(sb + wg * 1024, 2048), db = desc_lo(sb, 2560);
      mbar_wait(bars + 8 * B_ATTN, 0);
      mbar_wait(bars + 8 * (B_YST + 3), 0);
      mbar_wait(bars + 8 * (B_YST + 4), 0);
      if (PW2) mbar_wait(bars + 8 * B_FULL2, 0);
      TSM(w == 0, 15 + wg);
#pragma unroll 1
      for (int j = 0; j < 8; j++) {
        mbar_wait(bars + 8 * (B_FULL2 + j), 0);
        const uint32_t oa = da + (off_o(j) >> 4), ob = db + (off_w(j) >> 4);
        wg_fence();
#pragma unroll
        for (int k = 0; k < 5; k++) WgSST<80>::mma<HI_NONE, HI_SW32>(acc, oa + 256 * k, ob + 32 * k, 1);
        wg_commit();
        wg_wait<1>();
        if (j >= 1 && j <= 4 && lane == 0) mbar_arrive(bars + 8 * (B_EMPTY2 + j - 1));
      }
      TSIF(w == 0 && wg == 0, 113);
      const int tr = 64 * wg + 16 * w + (lane & 15);
      const uint32_t fm = sb + OFF_QS + tr * 128, fx = (lane >> 4) ^ (tr & 7);
      const uint32_t ft = sb + OFF_QT + tr * 32 + (((lane >> 4) ^ (tr >> 2)) & 1) * 16;
      const float g0 = __uint_as_float(lds32(sb + OFF_GATE + (64 * wg + 16 * w + g) * 4));
      const float g1 = __uint_as_float(lds32(sb + OFF_GATE + (64 * wg + 16 * w + 8 + g) * 4));
      const uint32_t ga = pack2(g0, g0), gb = pack2(g1, g1);
      const uint32_t na = pack2(1.f - g0, 1.f - g0), nb = pack2(1.f - g1, 1.f - g1);

      wg_wait<0>();
      pin<40>(acc);
      TSM(w == 0, 17 + wg);
      uint32_t pb[20];
#pragma unroll
      for (int j = 0; j < 10; j++) {
        pb[2 * j] = bmul(na, pack2(acc[4 * j], acc[4 * j + 1]));
        pb[2 * j + 1] = bmul(nb, pack2(acc[4 * j + 2], acc[4 * j + 3]));
        asm volatile("" : "+r"(pb[2 * j]), "+r"(pb[2 * j + 1]));
      }
      const uint32_t ya = sb + OFF_YT + wg * 10240 + ((lane >> 4) * 8 + (lane & 7)) * 128 +
                          (((2 * w + (((lane >> 3) & 1) ^ wg)) ^ (lane & 7)) << 4);
      uint32_t qf[20];
      mbar_wait(bars + 8 * B_QF, 0);
#pragma unroll
      for (int j = 0; j < 5; j++) ldsm4(qf + 4 * j, j < 4 ? fm + ((fx ^ (2 * j)) << 4) : ft);
      mbar_wait(bars + 8 * B_YFULL, 0);
      TSM(w == 0 && wg == 0, 19);
#pragma unroll
      for (int j = 0; j < 5; j++) {
        uint32_t y[4];
        ldsm4t(y, ya + 2048 * j);
#pragma unroll
        for (int i = 0; i < 4; i++) qf[4 * j + i] = badd(bmul((i & 1) ? gb : ga, bmul(qf[4 * j + i], y[i])), pb[4 * j + i]);
      }
#pragma unroll
      for (int j = 0; j < 5; j++) stsm4(j < 4 ? fm + ((fx ^ (2 * j)) << 4) : ft, qf + 4 * j);
      fence_async_smem();
      __syncwarp();
      if (lane == 0) {
        const int row = 64 * wg + 16 * w;
        asm volatile("cp.async.bulk.tensor.2d.global.shared::cta.bulk_group [%0, {%2, %3}], [%1];"
                     ::"l"(&m.om), "r"(sb + OFF_QS + row * 128), "r"(80 * hg), "r"(128 * r + row) : "memory");
        asm volatile("cp.async.bulk.tensor.2d.global.shared::cta.bulk_group [%0, {%2, %3}], [%1];"
                     ::"l"(&m.ot), "r"(sb + OFF_QT + row * 32), "r"(80 * hg + 64), "r"(128 * r + row) : "memory");
        asm volatile("cp.async.bulk.commit_group;\ncp.async.bulk.wait_group.read 0;" ::: "memory");
      }
      TSM(true, 40 + 4 * wg + w);
      if (ENDBAR) asm volatile("bar.sync 15, 256;" ::: "memory");
    }
  }
}

typedef CUresult (*EncodeFn)(CUtensorMap*, CUtensorMapDataType, cuuint32_t, void*, const cuuint64_t*, const cuuint64_t*,
                             const cuuint32_t*, const cuuint32_t*, CUtensorMapInterleave, CUtensorMapSwizzle,
                             CUtensorMapL2promotion, CUtensorMapFloatOOBfill);

void encode(EncodeFn fn, CUtensorMap* tm, const void* base, int rank, const cuuint64_t* dims, const cuuint64_t* strides,
            const cuuint32_t* box, CUtensorMapSwizzle swz) {
  const cuuint32_t ones[3] = {1, 1, 1};
  fn(tm, CU_TENSOR_MAP_DATA_TYPE_BFLOAT16, rank, const_cast<void*>(base), dims, strides, box, ones,
     CU_TENSOR_MAP_INTERLEAVE_NONE, swz, CU_TENSOR_MAP_L2_PROMOTION_L2_128B, CU_TENSOR_MAP_FLOAT_OOB_FILL_NONE);
}

}

extern "C" void kernel_launch(void* const* d_in, const int* in_sizes, int n_in, void* d_out, int out_size) {
  (void)in_sizes; (void)n_in; (void)out_size;
  Params p;
  p.q = (const __nv_bfloat16*)d_in[0];
  p.k = (const __nv_bfloat16*)d_in[1];
  p.v = (const __nv_bfloat16*)d_in[2];
  p.shift_k = (const __nv_bfloat16*)d_in[3];
  p.ssm_k = (const __nv_bfloat16*)d_in[4];
  p.ssm_D = (const __nv_bfloat16*)d_in[5];
  p.wqkv = (const __nv_bfloat16*)d_in[7];
  p.wo = (const __nv_bfloat16*)d_in[8];
  p.gate_w = (const __nv_bfloat16*)d_in[9];
  p.out = (__nv_bfloat16*)d_out;
  p.zero = 0;

  static EncodeFn fn = nullptr;
  static void *yaddr = nullptr, *uaddr = nullptr;
  if (!fn) {
    cudaDriverEntryPointQueryResult qr;
    void* f = nullptr;
    cudaGetDriverEntryPoint("cuTensorMapEncodeTiled", &f, cudaEnableDefault, &qr);
    fn = (EncodeFn)f;
    cudaGetSymbolAddress(&yaddr, g_Y);
    cudaGetSymbolAddress(&uaddr, g_U);
    cudaFuncSetAttribute(fused_kernel, cudaFuncAttributeMaxDynamicSharedMemorySize, SMEM_BYTES);
  }
  Maps m;
  {
    const cuuint64_t dims[3] = {640, 1024, 2}, st[2] = {2560, 1280};
    const cuuint32_t box[3] = {64, 64, 2};
    encode(fn, &m.x, p.q, 3, dims, st, box, CU_TENSOR_MAP_SWIZZLE_128B);
  }
  {
    const cuuint64_t dims[3] = {640, 640, 3}, st[2] = {3840, 1280};
    const cuuint32_t box[3] = {64, 64, 3}, boxt[3] = {16, 64, 3};
    encode(fn, &m.wm, p.wqkv, 3, dims, st, box, CU_TENSOR_MAP_SWIZZLE_128B);
    encode(fn, &m.wt, p.wqkv, 3, dims, st, boxt, CU_TENSOR_MAP_SWIZZLE_32B);
  }
  {
    const cuuint64_t dims[3] = {64, 2048, 10}, st[2] = {1280, 128};
    const cuuint32_t boxk[3] = {64, 35, 1}, boxv[3] = {64, 32, 1};
    encode(fn, &m.k, p.k, 3, dims, st, boxk, CU_TENSOR_MAP_SWIZZLE_128B);
    encode(fn, &m.v, p.v, 3, dims, st, boxv, CU_TENSOR_MAP_SWIZZLE_128B);
  }
  {
    const cuuint64_t dims[3] = {16, 640, 40}, st[2] = {1280, 32};
    const cuuint32_t box[3] = {16, 40, 5};
    encode(fn, &m.wo, p.wo, 3, dims, st, box, CU_TENSOR_MAP_SWIZZLE_32B);
  }
  {
    const cuuint64_t dims[2] = {2048, 640}, st[1] = {Y_PITCH * 16};
    const cuuint32_t box[2] = {64, 80};
    encode(fn, &m.y, yaddr, 2, dims, st, box, CU_TENSOR_MAP_SWIZZLE_128B);
    const cuuint64_t stu[1] = {U_PITCH * 16};
    const cuuint32_t boxu[2] = {32, 64};
    encode(fn, &m.u, uaddr, 2, dims, stu, boxu, CU_TENSOR_MAP_SWIZZLE_NONE);
  }
  {
    const cuuint64_t dims[2] = {640, 2048}, st[1] = {1280};
    const cuuint32_t bqm[2] = {64, 128}, bqt[2] = {16, 128}, bom[2] = {64, 16}, bot[2] = {16, 16};
    encode(fn, &m.qm, p.q, 2, dims, st, bqm, CU_TENSOR_MAP_SWIZZLE_128B);
    encode(fn, &m.qt, p.q, 2, dims, st, bqt, CU_TENSOR_MAP_SWIZZLE_32B);
    encode(fn, &m.om, p.out, 2, dims, st, bom, CU_TENSOR_MAP_SWIZZLE_128B);
    encode(fn, &m.ot, p.out, 2, dims, st, bot, CU_TENSOR_MAP_SWIZZLE_32B);
  }
  fused_kernel<<<NCTA, NTHR, SMEM_BYTES>>>(m, p);
}
```

```cpp
#include <cuda.h>
#include <cuda_bf16.h>
#include <cuda_runtime.h>
#include <stdint.h>

namespace {

constexpr int SEQ = 2048, DIM = 640, NCTA = 128, NTHR = 512;

#define TRIG_KB 9
#define KV_KB 2
#define DEV_EXIT 0
#define ATT_GATE 1
#define G_AFTER 0
#define FENCE_LO 0
#define FENCE_HI 0
#define PW1 2
#define PW2 1
#define ENDBAR 0
#define PAD_KB 0
#define Y_ALIAS 1
#define H_EARLY 1
#define NOMB 0
#define SRC_ROT 0
#define WAIT_NS 0
#define WB_TRIG B_USIG
#define G_POS 0
#define TAILF 1
#define T_ISSUE 384
#define T_PF 416
#define T_INIT 448
#define ATT_MERGE 0
#define BMAP 1
#define PRE2 1
#define KV_MIX 0
#define O_DEFER 0
#define TASK0 0x52
#define TASK1 0x3
#define TASK2 0x41
#define HALO_FIRST 1
#define PREV_EARLY 0
#define SKIP 0
#define ACQ 0
#define U_TMA 0
#define U_GATE 0
#define RF_GATE 0
#define WO_TRIG B_WST
#define WL_TRIG B_WOP
#define WO_GATE 1

constexpr uint32_t STAGE_BYTES = 47104, ST_W = 16384, ST_WT = 40960;
constexpr uint32_t O_BYTES = 20480, WO_BYTES = 12800;
constexpr uint32_t OFF_OA = 0;
constexpr uint32_t OFF_QS = 3 * O_BYTES, OFF_QT = OFF_QS + 16384;
constexpr uint32_t OFF_WC = 81920;
constexpr uint32_t OFF_WA = 94720;
constexpr uint32_t OFF_GATE = 145920;
constexpr uint32_t OFF_TT = 146432;
constexpr uint32_t OFF_KVX = 148480;
constexpr uint32_t OFF_CH3 = 163840;
constexpr uint32_t CH_BYTES = 12288, U_BYTES = 4096;
constexpr uint32_t OFF_FT = 225280, OFF_GT = 229376;
constexpr uint32_t OFF_CH0 = 188416;
constexpr uint32_t OFF_KVS = OFF_CH0, KVS_V = 4480, KVS_BYTES = 8576;
constexpr uint32_t OFF_WS = OFF_WA;
__device__ __forceinline__ uint32_t off_us(int s) { return OFF_CH0 + 4096 * ((0x65320 >> (4 * s)) & 7); }
constexpr uint32_t OFF_YT = 163840;
constexpr uint32_t OFF_BAR = 231936;
constexpr uint32_t SMEM_BYTES = OFF_BAR + 512;

enum : uint32_t {
  B_FULL1 = 0, B_EMPTY1 = 4, B_S3 = 7, B_FULL2 = 52, B_EMPTY2 = 13, B_U = 8, B_GATE = 12, B_HA = 19, B_HB = 20,
  B_ATTN = 21, B_C34 = 22, B_CONV = 23, B_YFULL = 24, B_EPOCH = 25, B_PREP = 26, B_P1 = 27, B_LAST = 28,
  B_E3 = 29, B_OSIG = 30, B_WOP = 31, B_USIG = 32, B_WST = 33, B_KV = 34, B_KVD = 39, B_QF = 17, B_YST = 40,
  B_US = 45, B_YSIG = 50
};
constexpr uint32_t OFF_EPOCH = OFF_BAR + 8 * 51, OFF_D = OFF_BAR + 8 * 60;
__device__ __forceinline__ uint32_t off_o(int j) { return j < 4 ? OFF_OA + j * O_BYTES : j < 6 ? OFF_CH0 + (j - 4) * O_BYTES : OFF_OA + (j - 6) * O_BYTES; }
__device__ __forceinline__ uint32_t off_w(int j) { return j < 4 ? OFF_WA + j * WO_BYTES : j == 4 ? OFF_KVX : j == 5 ? OFF_WC : OFF_WA + (j - 6) * WO_BYTES; }
__device__ __forceinline__ int step_src(int hg, int j) { return SRC_ROT ? (hg + j) & 7 : j == 0 ? hg : j <= hg ? j - 1 : j; }
__device__ __forceinline__ bool tail_first(int hg) { return TAILF && (hg & 3) == 3; }
__device__ __forceinline__ uint32_t off_ch(int c) { return (c < 3 ? OFF_CH0 : OFF_CH3 - 3 * CH_BYTES) + c * CH_BYTES; }

#define U_PITCH 264
__device__ __align__(1024) uint4 g_U[DIM * U_PITCH];
__device__ uint4 g_O[NCTA * 1280];
#define g_Y g_U
constexpr int Y_PITCH = U_PITCH;
__device__ uint4 g_WO[64 * 800];
__device__ uint4 g_halo[NCTA * 2 * 7 * 32];
__device__ float g_gate[SEQ + PAD_KB * 256];
__device__ unsigned g_cnt[32 * (1 + 2 * 16 + 8 + NCTA)];
constexpr int C_LAUNCH = 0, C_PREP = 32, C_Y = 32 * 17, C_W = 32 * 33, C_O = 32 * 41;

#define TSM(cond, slot) do { } while (0)
#define TSIF(cond, slot) do { if (__LINE__ >= FENCE_LO && __LINE__ < FENCE_HI) sched_fence(); } while (0)
__device__ __forceinline__ void sched_fence() {
  asm volatile("{\n.reg .pred p;\n.reg .u32 c;\nmov.u32 c, %%clock;\nsetp.eq.u32 p, c, 0;\n@p st.shared.u32 [%0], c;\n}"
               ::"r"(1024 + OFF_EPOCH + 4) : "memory");
}
#define TS(slot) TSIF(true, slot)

struct Params {
  const __nv_bfloat16 *q, *k, *v, *shift_k, *ssm_k, *ssm_D, *wqkv, *wo, *gate_w;
  __nv_bfloat16* out;
  uint32_t zero;
};

#define POLL_NS 0
constexpr int SPIN_LIMIT = 1 << 17;

__device__ __forceinline__ void mbar_init(uint32_t bar, uint32_t count) {
  asm volatile("mbarrier.init.shared::cta.b64 [%0], %1;" ::"r"(bar), "r"(count) : "memory");
}
__device__ __forceinline__ void mbar_expect_tx(uint32_t bar, uint32_t bytes) {
  asm volatile("mbarrier.arrive.expect_tx.shared::cta.b64 _, [%0], %1;" ::"r"(bar), "r"(bytes) : "memory");
}
__device__ __forceinline__ void mbar_arrive(uint32_t bar) {
  asm volatile("mbarrier.arrive.shared::cta.b64 _, [%0];" ::"r"(bar) : "memory");
}
__device__ __forceinline__ void mbar_wait(uint32_t bar, uint32_t parity) {
  uint32_t ok;
  int spins = 0;
  do {
    if (WAIT_NS)
      asm volatile("{\n.reg .pred p;\nmbarrier.try_wait.parity.shared::cta.b64 p, [%1], %2, %3;\nselp.b32 %0, 1, 0, p;\n}"
                   : "=r"(ok) : "r"(bar), "r"(parity), "r"(WAIT_NS) : "memory");
    else
      asm volatile("{\n.reg .pred p;\nmbarrier.try_wait.parity.shared::cta.b64 p, [%1], %2;\nselp.b32 %0, 1, 0, p;\n}"
                   : "=r"(ok) : "r"(bar), "r"(parity) : "memory");
    if (++spins > SPIN_LIMIT) break;
  } while (!ok);
}
__device__ __forceinline__ unsigned flag_read(const unsigned* p) {
  unsigned v;
  asm volatile("ld.relaxed.gpu.global.u32 %0, [%1];" : "=r"(v) : "l"(p) : "memory");
  return v;
}
__device__ __forceinline__ void flag_poll(const unsigned* p, unsigned target) {
  unsigned v;
  int spins = 0;
  do {
    if (POLL_NS && spins) __nanosleep(POLL_NS);
    asm volatile("ld.relaxed.gpu.global.u32 %0, [%1];" : "=r"(v) : "l"(p) : "memory");
    if (++spins > SPIN_LIMIT) break;
  } while ((int)(v - target) < 0);
}
__device__ __forceinline__ void flag_wait(const unsigned* p, unsigned target) {
  flag_poll(p, target);
  if (ACQ) asm volatile("fence.acquire.gpu;\nfence.proxy.async.global;" ::: "memory");
}
__device__ __forceinline__ void flag_signal(unsigned* p, int n, int lane) {
  if (lane == 0) asm volatile("fence.release.gpu;" ::: "memory");
  __syncwarp();
  if (lane < n) asm volatile("red.relaxed.gpu.global.add.u32 [%0], 1;" ::"l"(p + 32 * lane) : "memory");
}
__device__ __forceinline__ void flag_bump(unsigned* p) {
  asm volatile("red.relaxed.gpu.global.add.u32 [%0], 1;" ::"l"(p) : "memory");
}
__device__ __forceinline__ void fence_async_smem() { asm volatile("fence.proxy.async.shared::cta;" ::: "memory"); }
__device__ __forceinline__ void wg_sync(int id) { asm volatile("bar.sync %0, 128;" ::"r"(id) : "memory"); }

__device__ __forceinline__ void tma_2d(uint32_t dst, const CUtensorMap* tm, int c0, int c1, uint32_t bar) {
  asm volatile("cp.async.bulk.tensor.2d.shared::cluster.global.mbarrier::complete_tx::bytes [%0], [%1, {%3, %4}], [%2];"
               ::"r"(dst), "l"(tm), "r"(bar), "r"(c0), "r"(c1) : "memory");
}
__device__ __forceinline__ void tma_3d(uint32_t dst, const CUtensorMap* tm, int c0, int c1, int c2, uint32_t bar) {
  asm volatile("cp.async.bulk.tensor.3d.shared::cluster.global.mbarrier::complete_tx::bytes [%0], [%1, {%3, %4, %5}], [%2];"
               ::"r"(dst), "l"(tm), "r"(bar), "r"(c0), "r"(c1), "r"(c2) : "memory");
}
__device__ __forceinline__ void bulk_load(uint32_t dst, const void* src, uint32_t bytes, uint32_t bar) {
  asm volatile("cp.async.bulk.shared::cluster.global.mbarrier::complete_tx::bytes [%0], [%1], %2, [%3];"
               ::"r"(dst), "l"(src), "r"(bytes), "r"(bar) : "memory");
}
__device__ __forceinline__ void tm_prefetch(const CUtensorMap* tm) {
  asm volatile("prefetch.tensormap [%0];" ::"l"(tm) : "memory");
}

__device__ __forceinline__ void wg_fence() { asm volatile("wgmma.fence.sync.aligned;" ::: "memory"); }
__device__ __forceinline__ void wg_commit() { asm volatile("wgmma.commit_group.sync.aligned;" ::: "memory"); }
template <int N> __device__ __forceinline__ void wg_wait() { asm volatile("wgmma.wait_group.sync.aligned %0;" ::"n"(N) : "memory"); }
__device__ __forceinline__ uint32_t desc_lo(uint32_t addr, uint32_t lbo) { return ((addr & 0x3FFFF) >> 4) | ((lbo >> 4) << 16); }
constexpr uint32_t desc_hi(uint32_t sbo, uint32_t swz) { return (sbo >> 4) | (swz << 30); }
constexpr uint32_t HI_SW128 = desc_hi(1024, 1), HI_SW64 = desc_hi(512, 2), HI_SW32 = desc_hi(256, 3), HI_NONE = desc_hi(128, 0);
template <int N> __device__ __forceinline__ void pin(float* d) {
#pragma unroll
  for (int i = 0; i < N; i++) asm volatile("" : "+f"(d[i])::"memory");
}

__device__ __forceinline__ uint32_t lds32(uint32_t a) {
  uint32_t v;
  asm volatile("ld.volatile.shared.u32 %0, [%1];" : "=r"(v) : "r"(a) : "memory");
  return v;
}
__device__ __forceinline__ uint4 ldg128(const void* a) {
  uint4 v;
  asm volatile("ld.global.nc.v4.u32 {%0, %1, %2, %3}, [%4];" : "=r"(v.x), "=r"(v.y), "=r"(v.z), "=r"(v.w) : "l"(a) : "memory");
  return v;
}
__device__ __forceinline__ uint2 ldg64(const void* a) {
  uint2 v;
  asm volatile("ld.global.nc.v2.u32 {%0, %1}, [%2];" : "=r"(v.x), "=r"(v.y) : "l"(a) : "memory");
  return v;
}
__device__ __forceinline__ void ldsm4(uint32_t* r, uint32_t a) {
  asm volatile("ldmatrix.sync.aligned.m8n8.x4.shared.b16 {%0, %1, %2, %3}, [%4];"
               : "=r"(r[0]), "=r"(r[1]), "=r"(r[2]), "=r"(r[3]) : "r"(a) : "memory");
}
__device__ __forceinline__ void ldsm4t(uint32_t* r, uint32_t a) {
  asm volatile("ldmatrix.sync.aligned.m8n8.x4.trans.shared.b16 {%0, %1, %2, %3}, [%4];"
               : "=r"(r[0]), "=r"(r[1]), "=r"(r[2]), "=r"(r[3]) : "r"(a) : "memory");
}
__device__ __forceinline__ uint4 lds128(uint32_t a) {
  uint4 v;
  asm volatile("ld.shared.v4.u32 {%0, %1, %2, %3}, [%4];" : "=r"(v.x), "=r"(v.y), "=r"(v.z), "=r"(v.w) : "r"(a) : "memory");
  return v;
}
__device__ __forceinline__ void sts128(uint32_t a, uint32_t x, uint32_t y, uint32_t z, uint32_t w) {
  asm volatile("st.shared.v4.u32 [%0], {%1, %2, %3, %4};" ::"r"(a), "r"(x), "r"(y), "r"(z), "r"(w) : "memory");
}
__device__ __forceinline__ void stsm4(uint32_t a, const uint32_t* r) {
  asm volatile("stmatrix.sync.aligned.m8n8.x4.shared.b16 [%0], {%1, %2, %3, %4};" ::"r"(a), "r"(r[0]), "r"(r[1]), "r"(r[2]), "r"(r[3]) : "memory");
}
__device__ __forceinline__ void stsm4t(uint32_t a, const uint32_t* r) {
  asm volatile("stmatrix.sync.aligned.m8n8.x4.trans.shared.b16 [%0], {%1, %2, %3, %4};" ::"r"(a), "r"(r[0]), "r"(r[1]), "r"(r[2]), "r"(r[3]) : "memory");
}
__device__ __forceinline__ uint32_t pack2(float lo, float hi) {
  uint32_t r;
  asm("cvt.rn.bf16x2.f32 %0, %1, %2;" : "=r"(r) : "f"(hi), "f"(lo));
  return r;
}
__device__ __forceinline__ uint32_t movm(uint32_t a) {
  uint32_t d;
  asm volatile("movmatrix.sync.aligned.m8n8.trans.b16 %0, %1;" : "=r"(d) : "r"(a));
  return d;
}
__device__ __forceinline__ uint32_t bmul(uint32_t a, uint32_t b) {
  uint32_t d;
  asm("mul.rn.bf16x2 %0, %1, %2;" : "=r"(d) : "r"(a), "r"(b));
  return d;
}
__device__ __forceinline__ uint32_t badd(uint32_t a, uint32_t b) {
  uint32_t d;
  asm("add.rn.bf16x2 %0, %1, %2;" : "=r"(d) : "r"(a), "r"(b));
  return d;
}
__device__ __forceinline__ float bf_lo(uint32_t x) { return __uint_as_float(x << 16); }
__device__ __forceinline__ float bf_hi(uint32_t x) { return __uint_as_float(x & 0xFFFF0000u); }
__device__ __forceinline__ float ex2(float x) {
  float y;
  asm("ex2.approx.ftz.f32 %0, %1;" : "=f"(y) : "f"(x));
  return y;
}
__device__ __forceinline__ float rcp(float x) {
  float y;
  asm("rcp.approx.ftz.f32 %0, %1;" : "=f"(y) : "f"(x));
  return y;
}
__device__ __forceinline__ void mma16816(float* d, uint32_t a0, uint32_t a1, uint32_t a2, uint32_t a3, uint32_t b0, uint32_t b1) {
  asm volatile("mma.sync.aligned.m16n8k16.row.col.f32.bf16.bf16.f32 {%0, %1, %2, %3}, {%4, %5, %6, %7}, {%8, %9}, {%0, %1, %2, %3};"
               : "+f"(d[0]), "+f"(d[1]), "+f"(d[2]), "+f"(d[3])
               : "r"(a0), "r"(a1), "r"(a2), "r"(a3), "r"(b0), "r"(b1));
}
__device__ __forceinline__ void mma1688(float* d, uint32_t a0, uint32_t a1, uint32_t b0) {
  asm volatile("mma.sync.aligned.m16n8k8.row.col.f32.bf16.bf16.f32 {%0, %1, %2, %3}, {%4, %5}, {%6}, {%0, %1, %2, %3};"
               : "+f"(d[0]), "+f"(d[1]), "+f"(d[2]), "+f"(d[3])
               : "r"(a0), "r"(a1), "r"(b0));
}

template <int N> struct WgRS;
template <int N> struct WgSST;
template <> struct WgRS<32> {
  template <uint32_t HB>
  static __device__ __forceinline__ void mma(float* d, const uint32_t* a, uint32_t db) {
    asm volatile("{\n.reg .pred p;\n.reg .b64 db;\nsetp.ne.b32 p, %22, 0;\n"
      "mov.b64 db, {%20, %21};\n"
      "wgmma.mma_async.sync.aligned.m64n32k16.f32.bf16.bf16 {"
      "%0, %1, %2, %3, %4, %5, %6, %7, %8, %9, %10, %11, %12, %13, %14, %15"
      "}, {%16, %17, %18, %19}, db, p, 1, 1, 1;\n}\n"
      : "+f"(d[0]), "+f"(d[1]), "+f"(d[2]), "+f"(d[3]), "+f"(d[4]), "+f"(d[5]), "+f"(d[6]), "+f"(d[7]),
        "+f"(d[8]), "+f"(d[9]), "+f"(d[10]), "+f"(d[11]), "+f"(d[12]), "+f"(d[13]), "+f"(d[14]), "+f"(d[15])
      : "r"(a[0]), "r"(a[1]), "r"(a[2]), "r"(a[3]), "r"(db), "n"(HB), "n"(1));
  }
  template <uint32_t HB>
  static __device__ __forceinline__ void set(float* d, const uint32_t* a, uint32_t db) {
    asm volatile("{\n.reg .pred p;\n.reg .b64 db;\nsetp.ne.b32 p, %22, 0;\n"
      "mov.b64 db, {%20, %21};\n"
      "wgmma.mma_async.sync.aligned.m64n32k16.f32.bf16.bf16 {"
      "%0, %1, %2, %3, %4, %5, %6, %7, %8, %9, %10, %11, %12, %13, %14, %15"
      "}, {%16, %17, %18, %19}, db, p, 1, 1, 1;\n}\n"
      : "=f"(d[0]), "=f"(d[1]), "=f"(d[2]), "=f"(d[3]), "=f"(d[4]), "=f"(d[5]), "=f"(d[6]), "=f"(d[7]),
        "=f"(d[8]), "=f"(d[9]), "=f"(d[10]), "=f"(d[11]), "=f"(d[12]), "=f"(d[13]), "=f"(d[14]), "=f"(d[15])
      : "r"(a[0]), "r"(a[1]), "r"(a[2]), "r"(a[3]), "r"(db), "n"(HB), "n"(0));
  }
};
template <> struct WgRS<64> {
  template <uint32_t HB>
  static __device__ __forceinline__ void mma(float* d, const uint32_t* a, uint32_t db) {
    asm volatile("{\n.reg .pred p;\n.reg .b64 db;\nsetp.ne.b32 p, %38, 0;\n"
      "mov.b64 db, {%36, %37};\n"
      "wgmma.mma_async.sync.aligned.m64n64k16.f32.bf16.bf16 {"
      "%0, %1, %2, %3, %4, %5, %6, %7, %8, %9, %10, %11, %12, %13, %14, %15, "
      "%16, %17, %18, %19, %20, %21, %22, %23, %24, %25, %26, %27, %28, %29, %30, %31"
      "}, {%32, %33, %34, %35}, db, p, 1, 1, 1;\n}\n"
      : "+f"(d[0]), "+f"(d[1]), "+f"(d[2]), "+f"(d[3]), "+f"(d[4]), "+f"(d[5]), "+f"(d[6]), "+f"(d[7]),
        "+f"(d[8]), "+f"(d[9]), "+f"(d[10]), "+f"(d[11]), "+f"(d[12]), "+f"(d[13]), "+f"(d[14]), "+f"(d[15]),
        "+f"(d[16]), "+f"(d[17]), "+f"(d[18]), "+f"(d[19]), "+f"(d[20]), "+f"(d[21]), "+f"(d[22]), "+f"(d[23]),
        "+f"(d[24]), "+f"(d[25]), "+f"(d[26]), "+f"(d[27]), "+f"(d[28]), "+f"(d[29]), "+f"(d[30]), "+f"(d[31])
      : "r"(a[0]), "r"(a[1]), "r"(a[2]), "r"(a[3]), "r"(db), "n"(HB), "n"(1));
  }
  template <uint32_t HB>
  static __device__ __forceinline__ void set(float* d, const uint32_t* a, uint32_t db) {
    asm volatile("{\n.reg .pred p;\n.reg .b64 db;\nsetp.ne.b32 p, %38, 0;\n"
      "mov.b64 db, {%36, %37};\n"
      "wgmma.mma_async.sync.aligned.m64n64k16.f32.bf16.bf16 {"
      "%0, %1, %2, %3, %4, %5, %6, %7, %8, %9, %10, %11, %12, %13, %14, %15, "
      "%16, %17, %18, %19, %20, %21, %22, %23, %24, %25, %26, %27, %28, %29, %30, %31"
      "}, {%32, %33, %34, %35}, db, p, 1, 1, 1;\n}\n"
      : "=f"(d[0]), "=f"(d[1]), "=f"(d[2]), "=f"(d[3]), "=f"(d[4]), "=f"(d[5]), "=f"(d[6]), "=f"(d[7]),
        "=f"(d[8]), "=f"(d[9]), "=f"(d[10]), "=f"(d[11]), "=f"(d[12]), "=f"(d[13]), "=f"(d[14]), "=f"(d[15]),
        "=f"(d[16]), "=f"(d[17]), "=f"(d[18]), "=f"(d[19]), "=f"(d[20]), "=f"(d[21]), "=f"(d[22]), "=f"(d[23]),
        "=f"(d[24]), "=f"(d[25]), "=f"(d[26]), "=f"(d[27]), "=f"(d[28]), "=f"(d[29]), "=f"(d[30]), "=f"(d[31])
      : "r"(a[0]), "r"(a[1]), "r"(a[2]), "r"(a[3]), "r"(db), "n"(HB), "n"(0));
  }
};
template <> struct WgSST<48> {
  template <uint32_t HA, uint32_t HB>
  static __device__ __forceinline__ void mma(float* d, uint32_t da, uint32_t db, int sc) {
    asm volatile("{\n.reg .pred p;\n.reg .b64 da, db;\nsetp.ne.b32 p, %28, 0;\n"
      "mov.b64 da, {%24, %25};\nmov.b64 db, {%26, %27};\n"
      "wgmma.mma_async.sync.aligned.m64n48k16.f32.bf16.bf16 {"
      "%0, %1, %2, %3, %4, %5, %6, %7, %8, %9, %10, %11, %12, %13, %14, %15, "
      "%16, %17, %18, %19, %20, %21, %22, %23"
      "}, da, db, p, 1, 1, 0, 1;\n}\n"
      : "+f"(d[0]), "+f"(d[1]), "+f"(d[2]), "+f"(d[3]), "+f"(d[4]), "+f"(d[5]), "+f"(d[6]), "+f"(d[7]),
        "+f"(d[8]), "+f"(d[9]), "+f"(d[10]), "+f"(d[11]), "+f"(d[12]), "+f"(d[13]), "+f"(d[14]), "+f"(d[15]),
        "+f"(d[16]), "+f"(d[17]), "+f"(d[18]), "+f"(d[19]), "+f"(d[20]), "+f"(d[21]), "+f"(d[22]), "+f"(d[23])
      : "r"(da), "n"(HA), "r"(db), "n"(HB), "r"(sc));
  }
};
template <> struct WgSST<80> {
  template <uint32_t HA, uint32_t HB>
  static __device__ __forceinline__ void mma(float* d, uint32_t da, uint32_t db, int sc) {
    asm volatile("{\n.reg .pred p;\n.reg .b64 da, db;\nsetp.ne.b32 p, %44, 0;\n"
      "mov.b64 da, {%40, %41};\nmov.b64 db, {%42, %43};\n"
      "wgmma.mma_async.sync.aligned.m64n80k16.f32.bf16.bf16 {"
      "%0, %1, %2, %3, %4, %5, %6, %7, %8, %9, %10, %11, %12, %13, %14, %15, "
      "%16, %17, %18, %19, %20, %21, %22, %23, %24, %25, %26, %27, %28, %29, %30, %31, "
      "%32, %33, %34, %35, %36, %37, %38, %39"
      "}, da, db, p, 1, 1, 0, 1;\n}\n"
      : "+f"(d[0]), "+f"(d[1]), "+f"(d[2]), "+f"(d[3]), "+f"(d[4]), "+f"(d[5]), "+f"(d[6]), "+f"(d[7]),
        "+f"(d[8]), "+f"(d[9]), "+f"(d[10]), "+f"(d[11]), "+f"(d[12]), "+f"(d[13]), "+f"(d[14]), "+f"(d[15]),
        "+f"(d[16]), "+f"(d[17]), "+f"(d[18]), "+f"(d[19]), "+f"(d[20]), "+f"(d[21]), "+f"(d[22]), "+f"(d[23]),
        "+f"(d[24]), "+f"(d[25]), "+f"(d[26]), "+f"(d[27]), "+f"(d[28]), "+f"(d[29]), "+f"(d[30]), "+f"(d[31]),
        "+f"(d[32]), "+f"(d[33]), "+f"(d[34]), "+f"(d[35]), "+f"(d[36]), "+f"(d[37]), "+f"(d[38]), "+f"(d[39])
      : "r"(da), "n"(HA), "r"(db), "n"(HB), "r"(sc));
  }
};
template <> struct WgSST<192> {
  template <uint32_t HA, uint32_t HB>
  static __device__ __forceinline__ void mma(float* d, uint32_t da, uint32_t db, int sc) {
    asm volatile("{\n.reg .pred p;\n.reg .b64 da, db;\nsetp.ne.b32 p, %100, 0;\n"
      "mov.b64 da, {%96, %97};\nmov.b64 db, {%98, %99};\n"
      "wgmma.mma_async.sync.aligned.m64n192k16.f32.bf16.bf16 {"
      "%0, %1, %2, %3, %4, %5, %6, %7, %8, %9, %10, %11, %12, %13, %14, %15, "
      "%16, %17, %18, %19, %20, %21, %22, %23, %24, %25, %26, %27, %28, %29, %30, %31, "
      "%32, %33, %34, %35, %36, %37, %38, %39, %40, %41, %42, %43, %44, %45, %46, %47, "
      "%48, %49, %50, %51, %52, %53, %54, %55, %56, %57, %58, %59, %60, %61, %62, %63, "
      "%64, %65, %66, %67, %68, %69, %70, %71, %72, %73, %74, %75, %76, %77, %78, %79, "
      "%80, %81, %82, %83, %84, %85, %86, %87, %88, %89, %90, %91, %92, %93, %94, %95"
      "}, da, db, p, 1, 1, 0, 1;\n}\n"
      : "+f"(d[0]), "+f"(d[1]), "+f"(d[2]), "+f"(d[3]), "+f"(d[4]), "+f"(d[5]), "+f"(d[6]), "+f"(d[7]),
        "+f"(d[8]), "+f"(d[9]), "+f"(d[10]), "+f"(d[11]), "+f"(d[12]), "+f"(d[13]), "+f"(d[14]), "+f"(d[15]),
        "+f"(d[16]), "+f"(d[17]), "+f"(d[18]), "+f"(d[19]), "+f"(d[20]), "+f"(d[21]), "+f"(d[22]), "+f"(d[23]),
        "+f"(d[24]), "+f"(d[25]), "+f"(d[26]), "+f"(d[27]), "+f"(d[28]), "+f"(d[29]), "+f"(d[30]), "+f"(d[31]),
        "+f"(d[32]), "+f"(d[33]), "+f"(d[34]), "+f"(d[35]), "+f"(d[36]), "+f"(d[37]), "+f"(d[38]), "+f"(d[39]),
        "+f"(d[40]), "+f"(d[41]), "+f"(d[42]), "+f"(d[43]), "+f"(d[44]), "+f"(d[45]), "+f"(d[46]), "+f"(d[47]),
        "+f"(d[48]), "+f"(d[49]), "+f"(d[50]), "+f"(d[51]), "+f"(d[52]), "+f"(d[53]), "+f"(d[54]), "+f"(d[55]),
        "+f"(d[56]), "+f"(d[57]), "+f"(d[58]), "+f"(d[59]), "+f"(d[60]), "+f"(d[61]), "+f"(d[62]), "+f"(d[63]),
        "+f"(d[64]), "+f"(d[65]), "+f"(d[66]), "+f"(d[67]), "+f"(d[68]), "+f"(d[69]), "+f"(d[70]), "+f"(d[71]),
        "+f"(d[72]), "+f"(d[73]), "+f"(d[74]), "+f"(d[75]), "+f"(d[76]), "+f"(d[77]), "+f"(d[78]), "+f"(d[79]),
        "+f"(d[80]), "+f"(d[81]), "+f"(d[82]), "+f"(d[83]), "+f"(d[84]), "+f"(d[85]), "+f"(d[86]), "+f"(d[87]),
        "+f"(d[88]), "+f"(d[89]), "+f"(d[90]), "+f"(d[91]), "+f"(d[92]), "+f"(d[93]), "+f"(d[94]), "+f"(d[95])
      : "r"(da), "n"(HA), "r"(db), "n"(HB), "r"(sc));
  }
};

struct FftConst {
  uint32_t f[2][4], fi[4][4];
  float ta[4], tb[4];
};
__device__ __forceinline__ void cis(int m, float scale, float& c, float& s) {
  const float a = (float)m * (-6.283185307179586f * scale);
  c = __cosf(a);
  s = __sinf(a);
}
__device__ __forceinline__ void fft_tables(uint32_t (&v)[12], int tw) {
  const int row = tw >> 2, ch = tw & 3;
#pragma unroll
  for (int i = 0; i < 4; i++) {
    float c[2], s[2], x[2];
#pragma unroll
    for (int e = 0; e < 2; e++) {
      cis((((32 * (8 * ch + 2 * i + e) + 15) * (4 * row - 63) + 2048) & 4095) - 2048, 1.f / 4096, c[e], s[e]);
      float gc, gs;
      cis((((row & 15) * (8 * (ch & 1) + 2 * i + e) + 8) & 15) - 8, 1.f / 16, gc, gs);
      x[e] = (row >> 4) == (ch >> 1) ? gc : (ch >> 1) ? gs : -gs;
    }
    v[i] = pack2(c[0] * 0.125f, c[1] * 0.125f);
    v[4 + i] = pack2(s[0] * 0.125f, s[1] * 0.125f);
    v[8 + i] = pack2(x[0], x[1]);
  }
#pragma unroll
  for (int i = 0; i < 12; i++) asm volatile("" : "+r"(v[i]));
}
__device__ __forceinline__ void fft_tables_store(const uint32_t (&v)[12], uint32_t sb, int tw) {
  const int row = tw >> 2;
  const uint32_t x = ((tw ^ (row >> 1)) & 3) << 4, a = sb + OFF_FT + (16 * (row >> 3) + (row & 7)) * 64 + x;
  sts128(a, v[0], v[1], v[2], v[3]);
  sts128(a + 512, v[4], v[5], v[6], v[7]);
  sts128(sb + OFF_GT + row * 64 + x, v[8], v[9], v[10], v[11]);
}
__device__ __forceinline__ void fft_twiddles(float (&v)[4], int tw) {
#pragma unroll
  for (int i = 0; i < 2; i++) {
    float c, s;
    cis((2 * (2 * (tw & 3) + i) - 15) * (4 * (tw >> 2) - 63), 1.f / 4096, c, s);
    v[2 * i] = __fdividef(-s, 1.f + c);
    v[2 * i + 1] = s;
  }
  pin<4>(v);
}
__device__ __forceinline__ void fft_matrices(FftConst& k, uint32_t sb, int w, int lane) {
  const uint32_t x = (lane >> 1) & 3;
  const uint4 t0 = lds128(sb + OFF_TT + 512 * w + 16 * lane), t1 = lds128(sb + OFF_TT + 512 * w + 16 * (lane ^ 3));
  k.ta[0] = __uint_as_float(t0.x); k.tb[0] = __uint_as_float(t0.y); k.ta[1] = __uint_as_float(t0.z); k.tb[1] = __uint_as_float(t0.w);
  k.ta[3] = __uint_as_float(t1.x); k.tb[3] = __uint_as_float(t1.y); k.ta[2] = __uint_as_float(t1.z); k.tb[2] = __uint_as_float(t1.w);
#pragma unroll
  for (int i = 0; i < 2; i++) {
    ldsm4(k.f[i], sb + OFF_FT + (16 * w + (lane & 15)) * 64 + (((2 * i + (lane >> 4)) ^ x) << 4));
    ldsm4t(k.fi[i], sb + OFF_FT + (32 * i + lane) * 64 + ((w ^ x) << 4));
#pragma unroll
    for (int j = 0; j < 4; j++) {
      k.fi[2 + i][j] = (j & 1) ? k.fi[i][j - 1] ^ 0x80008000u : k.fi[i][j + 1];
      asm volatile("" : "+r"(k.fi[2 + i][j]));
    }
  }
}
__device__ __forceinline__ void rot(bool inv, float& x, float& y, float a, float b) {
  x = fmaf(inv ? -a : a, y, x);
  y = fmaf(inv ? -b : b, x, y);
  x = fmaf(inv ? -a : a, y, x);
}
__device__ __forceinline__ void twiddle_fwd(uint32_t (&a)[4][4], float* d, const FftConst& k) {
#pragma unroll
  for (int q = 0; q < 4; q++)
#pragma unroll
    for (int j = 0; j < 2; j++) {
      float* x = d + 8 * q + 4 * j;
      rot(j, x[0], x[2], k.ta[2 * j], k.tb[2 * j]);
      rot(j, x[1], x[3], k.ta[2 * j + 1], k.tb[2 * j + 1]);
      a[q & 2][2 * j + (q & 1)] = pack2(x[0], x[1]);
      a[(q & 2) + 1][2 * j + (q & 1)] = pack2(x[2], x[3]);
    }
}
__device__ __forceinline__ void g_step(float* d, const uint32_t (&a)[4][4], uint32_t dre, uint32_t dim) {
  WgRS<32>::set<HI_SW64>(d, a[0], dre);
  WgRS<32>::set<HI_SW64>(d + 16, a[2], dre);
  WgRS<32>::mma<HI_SW64>(d, a[1], dim);
  WgRS<32>::mma<HI_SW64>(d + 16, a[3], dim);
  wg_commit();
}

__device__ __forceinline__ void conv_channel(const FftConst& k, uint32_t sb, int c, int wg, int w, int lane) {
  const uint32_t cb = sb + off_ch(c), bars = sb + OFF_BAR;
  const uint32_t du = desc_lo(cb, 1024), dg = desc_lo(sb + OFF_GT, 16), dz = desc_lo(cb + U_BYTES, 16);
  float U[32], H[32];
  uint32_t a[4][4], e[4][4];
  const float dv = __uint_as_float(lds32(sb + OFF_D + 4 * c));
  wg_fence();
  WgRS<64>::set<HI_SW32>(H, k.f[0], du + 256);
  WgRS<64>::mma<HI_SW32>(H, k.f[1], du + 256 + 32);
  wg_commit();
  wg_wait<0>();
  pin<32>(H);
  twiddle_fwd(a, H, k);
  if (ATT_GATE && H_EARLY) mbar_wait(bars + 8 * B_ATTN, 0);
  mbar_wait(bars + 8 * (B_U + (c < 3 ? c : 3)), 0);
  TSM(w == 0 && c < 3, 7 + wg);
  wg_fence();
  WgRS<64>::set<HI_SW32>(U, k.f[0], du);
  WgRS<64>::mma<HI_SW32>(U, k.f[1], du + 32);
  wg_commit();
  g_step(H, a, dg, dg + 64);
  wg_wait<1>();
  pin<32>(U);
  twiddle_fwd(e, U, k);
  wg_fence();
  g_step(U, e, dg, dg + 64);
  wg_wait<0>();
  pin<32>(U);
  pin<32>(H);
#pragma unroll
  for (int j = 0; j < 2; j++) {
    float pr[4][2], pi[4][2];
#pragma unroll
    for (int x = 0; x < 2; x++) {
      H[4 * j + x] += dv;
#pragma unroll
      for (int m = 0; m < 4; m++) {
#pragma unroll
        for (int q = 0; q <= m; q++) {
          const int ih = 16 * (q >> 1) + 2 * (q & 1) + 4 * j + x, iu = 16 * ((m - q) >> 1) + 2 * ((m - q) & 1) + 4 * j + x;
          pr[m][x] = q ? fmaf(H[ih], U[iu], pr[m][x]) : H[ih] * U[iu];
          pi[m][x] = q ? fmaf(H[ih], U[iu + 8], pi[m][x]) : H[ih] * U[iu + 8];
          pr[m][x] = fmaf(-H[ih + 8], U[iu + 8], pr[m][x]);
          pi[m][x] = fmaf(H[ih + 8], U[iu], pi[m][x]);
        }
      }
    }
#pragma unroll
    for (int m = 0; m < 4; m++) {
      a[m & 2][2 * j + (m & 1)] = pack2(pr[m][0], pr[m][1]);
      a[(m & 2) + 1][2 * j + (m & 1)] = pack2(pi[m][0], pi[m][1]);
    }
  }
  wg_fence();
  g_step(U, a, dg + 64, dg);
  const uint32_t za = cb + U_BYTES + (8 * w + (lane & 7)) * 128 + (((lane >> 3) ^ (lane & 7)) << 4);
  const uint32_t ya = cb + (lane >> 4) * 1024 + (8 * w + (lane & 7)) * 32 + ((((lane >> 3) ^ (lane >> 2)) & 1) << 4);
  wg_sync(1 + wg);
  wg_wait<0>();
  pin<32>(U);
  TSIF(w == 0, 80 + c);
#pragma unroll
  for (int p = 0; p < 2; p++) {
#pragma unroll
    for (int i = 0; i < 4; i++) {
      const int j = i & 1;
      float* x = U + 16 * p + 4 * j + (i & 2);
      rot(!j, x[8], x[0], k.ta[2 * j], k.tb[2 * j]);
      rot(!j, x[9], x[1], k.ta[2 * j + 1], k.tb[2 * j + 1]);
      e[p][i] = pack2(x[8], x[9]);
      e[2 + p][i] = pack2(x[0], x[1]);
    }
    stsm4(za ^ (64 * p), e[p]);
    stsm4((za ^ (64 * p)) + 4096, e[2 + p]);
  }
  fence_async_smem();
  wg_sync(1 + wg);
  wg_fence();
  WgRS<64>::set<HI_SW128>(H, k.fi[0], dz);
#pragma unroll
  for (int ks = 1; ks < 4; ks++) WgRS<64>::mma<HI_SW128>(H, k.fi[ks], dz + 128 * ks);
  wg_commit();
  wg_wait<0>();
  pin<32>(H);
  TSIF(w == 0, 88 + c);
#pragma unroll
  for (int j = 0; j < 8; j++)
    a[j >> 2][j & 3] = j < 2 ? pack2(H[4 * j], H[4 * j + 1]) : pack2(H[4 * j] + H[4 * j - 6], H[4 * j + 1] + H[4 * j - 5]);
  stsm4(ya, a[0]);
  stsm4(ya + 2048, a[1]);
  fence_async_smem();
  __syncwarp();
}

__device__ __forceinline__ void prep_slab(uint4* res, const uint2* sw, uint32_t sb, int slab, int w, int lane) {
  const int t = lane & 3, tp = (lane & 7) >> 1, pos = 8 * tp + 2 * (((lane >> 3) + tp) & 3) + (lane & 1);
  const uint32_t base = sb + OFF_KVS + slab * KVS_BYTES + pos * 128;
  uint32_t kk[2][4][4], vv[2][4];
  mbar_wait(sb + OFF_BAR + 8 * (B_KV + slab), 0);
#pragma unroll
  for (int h = 0; h < 2; h++) {
#pragma unroll
    for (int j = 0; j < 4; j++) {
      const uint32_t a = base + 128 * j;
      ldsm4t(kk[h][j], a + (((w + 4 * h) ^ ((a >> 7) & 7)) << 4));
    }
    const uint32_t a = base + KVS_V;
    ldsm4t(vv[h], a + (((w + 4 * h) ^ ((a >> 7) & 7)) << 4));
  }
#pragma unroll
  for (int h = 0; h < 2; h++) {
    uint32_t (&k)[4][4] = kk[h];
    uint32_t (&v)[4] = vv[h];
    const uint32_t w0 = __byte_perm(sw[h].x, 0, 0x1010), w1 = __byte_perm(sw[h].x, 0, 0x3232);
    const uint32_t w2 = __byte_perm(sw[h].y, 0, 0x1010), w3 = __byte_perm(sw[h].y, 0, 0x3232);
#pragma unroll
    for (int m = 0; m < 4; m++)
      v[m] = bmul(badd(badd(badd(bmul(k[0][m], w3), bmul(k[1][m], w2)), bmul(k[2][m], w1)), bmul(k[3][m], w0)), v[m]);
    uint32_t a[4];
#pragma unroll
    for (int m = 0; m < 4; m++) a[m] = (t & 1) ? v[(m + 3) & 3] : v[m];
    res[h] = (t & 2) ? make_uint4(a[2], a[3], a[0], a[1]) : make_uint4(a[0], a[1], a[2], a[3]);
  }
}

__device__ __forceinline__ void prep_gate(const Params& p, int b, int w, int lane) {
  uint2 gw[5], x[4][5];
#pragma unroll
  for (int j = 0; j < 5; j++) gw[j] = ldg64(reinterpret_cast<const uint2*>(p.gate_w) + lane + 32 * j);
#pragma unroll
  for (int i = 0; i < 4; i++)
#pragma unroll
    for (int j = 0; j < 5; j++)
      x[i][j] = ldg64(reinterpret_cast<const uint2*>(p.q) + (16 * b + 4 * w + i) * (DIM / 4) + lane + 32 * j);
  float s[4];
#pragma unroll
  for (int i = 0; i < 4; i++) {
    s[i] = 0.f;
#pragma unroll
    for (int j = 0; j < 5; j++) {
      const uint32_t m0 = bmul(x[i][j].x, gw[j].x), m1 = bmul(x[i][j].y, gw[j].y);
      s[i] += (bf_lo(m0) + bf_hi(m0)) + (bf_lo(m1) + bf_hi(m1));
    }
  }
  const bool h = lane & 16, q = lane & 8;
  const float a = (h ? s[2] : s[0]) + __shfl_xor_sync(0xffffffffu, h ? s[0] : s[2], 16);
  const float c = (h ? s[3] : s[1]) + __shfl_xor_sync(0xffffffffu, h ? s[1] : s[3], 16);
  float z = (q ? c : a) + __shfl_xor_sync(0xffffffffu, q ? a : c, 8);
#pragma unroll
  for (int o = 4; o > 0; o >>= 1) z += __shfl_xor_sync(0xffffffffu, z, o);
  z = bf_lo(pack2(z, 0.f));
  if ((lane & 7) == 0) g_gate[16 * b + 4 * w + (lane >> 3)] = bf_lo(pack2(__fdividef(1.f, 1.f + __expf(-z)), 0.f));
}

__device__ __forceinline__ uint32_t bmax(uint32_t a, uint32_t b) {
  uint32_t d;
  asm("max.bf16x2 %0, %1, %2;" : "=r"(d) : "r"(a), "r"(b));
  return d;
}
__device__ __forceinline__ void softmax_two(const float (&l)[2][2], uint32_t& p0, uint32_t& p1) {
  constexpr float kScale = 0.22360679774997896f, kLog2e = 1.4426950408889634f;
  const uint32_t r0 = pack2(l[0][0], l[1][0]), r1 = pack2(l[0][1], l[1][1]);
  const uint32_t x0 = pack2(bf_lo(r0) * kScale, bf_hi(r0) * kScale), x1 = pack2(bf_lo(r1) * kScale, bf_hi(r1) * kScale);
  uint32_t m = bmax(x0, x1);
  m = bmax(m, __shfl_xor_sync(0xffffffffu, m, 1));
  m = bmax(m, __shfl_xor_sync(0xffffffffu, m, 2));
  const float m0 = bf_lo(m) * kLog2e, m1 = bf_hi(m) * kLog2e;
  p0 = pack2(ex2(bf_lo(x0) * kLog2e - m0), ex2(bf_lo(x1) * kLog2e - m0));
  p1 = pack2(ex2(bf_hi(x0) * kLog2e - m1), ex2(bf_hi(x1) * kLog2e - m1));
}

__device__ __forceinline__ void halo_read(uint32_t (&kpv)[10], uint32_t (&vpv)[10], uint32_t (&tg)[7], const uint4* hp) {
#pragma unroll
  for (int j = 0; j < 7; j++) {
    uint32_t x0, x1, x2;
    asm volatile("ld.relaxed.gpu.global.v4.u32 {%0, %1, %2, %3}, [%4];"
                 : "=r"(x0), "=r"(x1), "=r"(x2), "=r"(tg[j]) : "l"(hp + 32 * j) : "memory");
    if (j < 4) kpv[3 * j] = x0; else vpv[3 * j - 10] = x0;
    if (j < 3) kpv[3 * j + 1] = x1; else vpv[3 * j - 9] = x1;
    if (j < 3) kpv[3 * j + 2] = x2; else if (j < 6) vpv[3 * j - 8] = x2;
  }
}

template <int ROT>
__device__ __forceinline__ void pack_qkv(const float* acc, uint32_t (&qlo)[10], uint32_t (&qhi)[10], uint32_t (&klo)[10],
                                         uint32_t (&khi)[10], uint32_t (&vlo)[10], uint32_t (&vhi)[10]) {
#pragma unroll
  for (int j = 0; j < 10; j++) {
    const int x = (j + ROT) % 10, tq = x < 8 ? x : 16 + x, tk = x < 8 ? 8 + x : 18 + x, tv = x < 8 ? 16 + x : 20 + x;
    khi[j] = pack2(acc[4 * tk + 2], acc[4 * tk + 3]);
    vhi[j] = movm(pack2(acc[4 * tv + 2], acc[4 * tv + 3]));
    qlo[j] = pack2(acc[4 * tq], acc[4 * tq + 1]);
    qhi[j] = pack2(acc[4 * tq + 2], acc[4 * tq + 3]);
    klo[j] = pack2(acc[4 * tk], acc[4 * tk + 1]);
    vlo[j] = pack2(acc[4 * tv], acc[4 * tv + 1]);
    asm volatile("" : "+r"(khi[j]), "+r"(qlo[j]), "+r"(qhi[j]), "+r"(klo[j]), "+r"(vlo[j]));
  }
}

template <int ROT> __device__ __forceinline__ void halo_send(const float* acc, uint4* ho, uint32_t tag) {
#pragma unroll
  for (int j = 0; j < 7; j++) {
    uint32_t x[3];
#pragma unroll
    for (int e = 0; e < 3; e++) {
      const int i = 3 * j + e, y = (i % 10 + ROT) % 10, tk = y < 8 ? 8 + y : 18 + y, tv = y < 8 ? 16 + y : 20 + y;
      x[e] = i < 10 ? pack2(acc[4 * tk + 2], acc[4 * tk + 3]) : i < 20 ? movm(pack2(acc[4 * tv + 2], acc[4 * tv + 3])) : 0u;
    }
    asm volatile("st.relaxed.gpu.global.v4.u32 [%0], {%1, %2, %3, %4};" ::"l"(ho + 32 * j), "r"(x[0]), "r"(x[1]), "r"(x[2]), "r"(tag) : "memory");
  }
}

__device__ __forceinline__ void attention(float* acc, uint32_t sb, int b, int par, int w, int lane, uint32_t tag) {
  const int g = lane >> 2, t = lane & 3;
  uint32_t klo[10], khi[10], vlo[10], vhi[10], qlo[10], qhi[10], kpv[10], vpv[10];
  if (HALO_FIRST && w == 3 && b < NCTA - 8) {
    uint4* ho = g_halo + (b * 2 + par) * 224 + lane;
    if (tail_first(b & 7)) halo_send<8>(acc, ho, tag);
    else halo_send<0>(acc, ho, tag);
    TSIF(par == 0, 76);
    pin<120>(acc);
  }
  if (tail_first(b & 7)) pack_qkv<8>(acc, qlo, qhi, klo, khi, vlo, vhi);
  else pack_qkv<0>(acc, qlo, qhi, klo, khi, vlo, vhi);
  const uint32_t xa = sb + OFF_KVX + (par * 3) * 2560 + lane * 16;
  if (w < 3) {
    sts128(xa + w * 2560, khi[0], khi[1], khi[2], khi[3]);
    sts128(xa + w * 2560 + 512, khi[4], khi[5], khi[6], khi[7]);
    sts128(xa + w * 2560 + 1024, khi[8], khi[9], vhi[0], vhi[1]);
    sts128(xa + w * 2560 + 1536, vhi[2], vhi[3], vhi[4], vhi[5]);
    sts128(xa + w * 2560 + 2048, vhi[6], vhi[7], vhi[8], vhi[9]);
  } else if (!HALO_FIRST && b < NCTA - 8) {
    uint4* ho = g_halo + (b * 2 + par) * 224 + lane;
#pragma unroll
    for (int j = 0; j < 7; j++) {
      const uint32_t x0 = j < 4 ? khi[3 * j] : vhi[3 * j - 10], x1 = j < 3 ? khi[3 * j + 1] : vhi[3 * j - 9];
      const uint32_t x2 = j < 3 ? khi[3 * j + 2] : j < 6 ? vhi[3 * j - 8] : 0u;
      asm volatile("st.relaxed.gpu.global.v4.u32 [%0], {%1, %2, %3, %4};" ::"l"(ho + 32 * j), "r"(x0), "r"(x1), "r"(x2), "r"(tag) : "memory");
    }
  }
  TSIF(par == 0 && w == 1, 64);
  TSIF(par == 0 && w == 3 && !HALO_FIRST, 76);
#pragma unroll
  for (int j = 0; j < 10; j++) vlo[j] = movm(vlo[j]);
  const bool far0 = 2 * t > g, far1 = 2 * t + 1 > g;
  const uint32_t mfar = (far0 ? 0x0000FFFFu : 0u) | (far1 ? 0xFFFF0000u : 0u);
  float slo[4][2], shi[4][2], lg[2][2];
  uint32_t phi[4], plo[4], qml[4], qmh[4];
#pragma unroll
  for (int h = 0; h < 4; h++) {
    const int f = h == 0 ? 0 : h == 1 ? 3 : h == 2 ? 5 : 8, hf = h < 2 ? 2 : 7;
    const bool mine = (h & 1) ? t >= 2 : t < 2;
    qml[h] = mine ? qlo[hf] : 0u;
    qmh[h] = mine ? qhi[hf] : 0u;
    float a[4] = {0.f, 0.f, 0.f, 0.f}, c[4] = {0.f, 0.f, 0.f, 0.f};
    mma16816(a, qlo[f], qhi[f], qlo[f + 1], qhi[f + 1], klo[f], klo[f + 1]);
    mma16816(c, qlo[f], qhi[f], qlo[f + 1], qhi[f + 1], khi[f], khi[f + 1]);
    mma1688(a, qml[h], qmh[h], klo[hf]);
    mma1688(c, qml[h], qmh[h], khi[hf]);
    slo[h][0] = a[0];
    slo[h][1] = a[1];
    shi[h][0] = lg[h & 1][0] = far0 ? a[2] : c[2];
    shi[h][1] = lg[h & 1][1] = far1 ? a[3] : c[3];
    if (!ATT_MERGE && (h & 1)) softmax_two(lg, phi[h - 1], phi[h]);
  }
  TSIF(par == 0 && w == 1, 65);
  wg_sync(1 + par);
  TSIF(par == 0 && w == 1, 66);
  const bool nohist = (w == 0) && (b < 8);
  const uint4* hp = g_halo + ((b - 8) * 2 + par) * 224 + lane;
  uint32_t tg[7];
  if (w > 0) {
    const uint4 v0 = lds128(xa + (w - 1) * 2560), v1 = lds128(xa + (w - 1) * 2560 + 512), v2 = lds128(xa + (w - 1) * 2560 + 1024);
    const uint4 v3 = lds128(xa + (w - 1) * 2560 + 1536), v4 = lds128(xa + (w - 1) * 2560 + 2048);
    kpv[0] = v0.x; kpv[1] = v0.y; kpv[2] = v0.z; kpv[3] = v0.w; kpv[4] = v1.x; kpv[5] = v1.y; kpv[6] = v1.z; kpv[7] = v1.w;
    kpv[8] = v2.x; kpv[9] = v2.y; vpv[0] = v2.z; vpv[1] = v2.w; vpv[2] = v3.x; vpv[3] = v3.y; vpv[4] = v3.z; vpv[5] = v3.w;
    vpv[6] = v4.x; vpv[7] = v4.y; vpv[8] = v4.z; vpv[9] = v4.w;
  } else if (nohist) {
#pragma unroll
    for (int j = 0; j < 10; j++) kpv[j] = vpv[j] = 0u;
  } else {
    TSIF(par == 0, 77);
    halo_read(kpv, vpv, tg, hp);
  }
  if (w == 0 && !nohist) {
    int spins = 0;
    while (true) {
      bool ok = true;
#pragma unroll
      for (int j = 0; j < 7; j++) ok = ok && tg[j] == tag;
      if (__all_sync(0xffffffffu, ok) || ++spins > SPIN_LIMIT) break;
      halo_read(kpv, vpv, tg, hp);
    }
    TSIF(par == 0, 79);
  }
#pragma unroll
  for (int h = 0; h < 4; h++) {
    const int f = h == 0 ? 0 : h == 1 ? 3 : h == 2 ? 5 : 8, hf = h < 2 ? 2 : 7;
    float a[4] = {0.f, 0.f, 0.f, 0.f};
    mma16816(a, qlo[f], qhi[f], qlo[f + 1], qhi[f + 1], kpv[f], kpv[f + 1]);
    mma1688(a, qml[h], qmh[h], kpv[hf]);
    const float ninf = __int_as_float(0xff800000);
    lg[h & 1][0] = far0 ? (nohist ? ninf : a[0]) : slo[h][0];
    lg[h & 1][1] = far1 ? (nohist ? ninf : a[1]) : slo[h][1];
    if (h & 1) {
      softmax_two(lg, plo[h - 1], plo[h]);
      if (ATT_MERGE) {
        const float lh[2][2] = {{shi[h - 1][0], shi[h - 1][1]}, {shi[h][0], shi[h][1]}};
        softmax_two(lh, phi[h - 1], phi[h]);
      }
    }
  }
  TSIF(par == 0 && w <= 1, 67 + w);
  uint32_t ov[20];
#pragma unroll
  for (int hp = 0; hp < 2; hp++) {
    const int hf = hp ? 7 : 2;
    float sh[4] = {0.f, 0.f, 0.f, 0.f}, i0 = 0.f, i1 = 0.f;
#pragma unroll
    for (int e = 0; e < 2; e++) {
      const int h = 2 * hp + e, f = h == 0 ? 0 : h == 1 ? 3 : h == 2 ? 5 : 8;
      const uint32_t a0 = plo[h] & mfar, a2 = plo[h] & ~mfar, a3 = phi[h] & mfar, c1 = phi[h] & ~mfar;
      float sum[4] = {0.f, 0.f, 0.f, 0.f};
      mma1688(sum, plo[h], phi[h], 0x3F803F80u);
      const float r0 = rcp(sum[0]), r1 = rcp(sum[2]);
#pragma unroll
      for (int j = f; j < f + 2; j++) {
        float o[4] = {0.f, 0.f, 0.f, 0.f};
        mma16816(o, a0, 0u, a2, a3, vpv[j], vlo[j]);
        mma1688(o, 0u, c1, vhi[j]);
        ov[2 * j] = pack2(o[0] * r0, o[1] * r0);
        ov[2 * j + 1] = pack2(o[2] * r1, o[3] * r1);
      }
      const bool mine = e ? g >= 4 : g < 4;
      mma16816(sh, a0, 0u, a2, a3, mine ? vpv[hf] : 0u, mine ? vlo[hf] : 0u);
      mma1688(sh, 0u, c1, mine ? vhi[hf] : 0u);
      if (e == 0 || t >= 2) {
        i0 = r0;
        i1 = r1;
      }
    }
    ov[2 * hf] = pack2(sh[0] * i0, sh[1] * i0);
    ov[2 * hf + 1] = pack2(sh[2] * i1, sh[3] * i1);
  }
  TS(32 + 4 * par + w);
  mbar_wait(sb + OFF_BAR + 8 * B_P1, 0);
  const uint32_t oa = sb + OFF_OA + (lane >> 4) * 2048 + (32 * w + 2 * (lane & 15) + par) * 16;
#pragma unroll
  for (int j = 0; j < 5; j++) stsm4(oa + 4096 * j, ov + 4 * j);
  TSIF(par == 0 && w == 0, 120);
  fence_async_smem();
  TSIF(par == 0 && w == 0, 121);
  __syncwarp();
  if (lane == 0) mbar_arrive(sb + OFF_BAR + 8 * B_ATTN);
  TSM(w == 0 || w == 2, 122 + par + (w == 2 ? 3 : 0));
}

struct Maps {
  CUtensorMap x, wm, wt, k, v, y, wo, qm, qt, om, ot, u;
};

__device__ __forceinline__ void load_stage(uint32_t sb, int kb, int b, const Maps& m) {
  const uint32_t st = sb + (kb & 3) * STAGE_BYTES, bar = sb + OFF_BAR + 8 * (B_FULL1 + (kb & 3));
  const int r = b >> 3, hg = b & 7, slab = kb - KV_KB;
  const bool kv = slab >= 0 && slab < 5;
  const uint32_t kbar = sb + OFF_BAR + 8 * (B_KV + slab), dst = sb + OFF_KVS + slab * KVS_BYTES;
  mbar_expect_tx(bar, STAGE_BYTES);
  if (kv) mbar_expect_tx(kbar, KVS_BYTES);
  tma_3d(st, &m.x, 64 * kb, 64 * r, 0, bar);
  if (kv && KV_MIX) tma_3d(dst, &m.k, 0, 32 * (b >> 1) - 3, 2 * slab + (b & 1), kbar);
  tma_3d(st + ST_W, &m.wm, 80 * hg + (tail_first(hg) ? 16 : 0), 64 * kb, 0, bar);
  if (kv && KV_MIX) tma_3d(dst + KVS_V, &m.v, 0, 32 * (b >> 1), 2 * slab + (b & 1), kbar);
  tma_3d(st + ST_WT, &m.wt, 80 * hg + (tail_first(hg) ? 0 : 64), 64 * kb, 0, bar);
  if (kv && !KV_MIX) tma_3d(dst, &m.k, 0, 32 * (b >> 1) - 3, 2 * slab + (b & 1), kbar);
  if (kv && !KV_MIX) tma_3d(dst + KVS_V, &m.v, 0, 32 * (b >> 1), 2 * slab + (b & 1), kbar);
}

__global__ void __launch_bounds__(NTHR, 1) fused_kernel(const __grid_constant__ Maps m, const Params p) {
  extern __shared__ __align__(1024) uint8_t smem[];
  const uint32_t sb = (uint32_t)__cvta_generic_to_shared(smem);
  const uint32_t bars = sb + OFF_BAR;
  const int tid = threadIdx.x, lane = tid & 31;
  int b = blockIdx.x;
  if (BMAP == 1) b = (((b & 63) >> 3) * 2 + (b & 1)) * 8 + (((b < 64 ? 0x6521 : 0x7430) >> (4 * ((b >> 1) & 3))) & 7);
  if (BMAP == 2) b = ((b & 63) >> 2) * 8 + (((b < 64 ? 0x6521 : 0x7430) >> (4 * (b & 3))) & 7);
  if (BMAP == 3) b = (((b & 63) >> 3) * 2 + (b & 1)) * 8 + (((b < 64 ? 0x7430 : 0x6521) >> (4 * ((b >> 1) & 3))) & 7);
  if (BMAP == 4) b = (((b >> 4) * 2 + (b & 1)) * 8) + ((b >> 1) & 7);
  if (BMAP == 5) b = 127 - b;
  const int r = b >> 3, hg = b & 7;

  if (tid == T_ISSUE) {
    TSM(true, 0);
#pragma unroll
    for (int i = 0; i < 4; i++) mbar_init(bars + 8 * (B_FULL1 + i), 1);
#pragma unroll
    for (int i = 0; i < 3; i++) mbar_init(bars + 8 * (B_KV + i), 1);
    fence_async_smem();
#pragma unroll 1
    for (int kb = 0; kb <= PRE2; kb++) load_stage(sb, kb, b, m);
  } else if (tid >= T_PF && tid < T_PF + 12) {
    tm_prefetch(&m.x + (tid - T_PF));
  } else if (tid == T_INIT) {
#pragma unroll
    for (int i = 0; i < 4; i++) mbar_init(bars + 8 * (B_EMPTY1 + i), 8);
#pragma unroll
    for (int i = 0; i < 8; i++) mbar_init(bars + 8 * (B_FULL2 + i), 1);
#pragma unroll
    for (int i = 0; i < 4; i++) mbar_init(bars + 8 * (B_EMPTY2 + i), 8);
#pragma unroll
    for (int i = 0; i < 4; i++) mbar_init(bars + 8 * (B_U + i), 1);
    mbar_init(bars + 8 * B_HA, 4);
    mbar_init(bars + 8 * B_GATE, 4);
    mbar_init(bars + 8 * B_HB, 1);
    mbar_init(bars + 8 * B_KVD, 4);
    mbar_init(bars + 8 * B_QF, 1);
    mbar_init(bars + 8 * B_ATTN, 8);
    mbar_init(bars + 8 * B_P1, 8);
    mbar_init(bars + 8 * B_C34, 1);
#pragma unroll
    for (int i = 0; i < 5; i++) mbar_init(bars + 8 * (B_YST + i), 4);
#pragma unroll
    for (int i = 0; i < 5; i++) mbar_init(bars + 8 * (B_US + i), 4);
    mbar_init(bars + 8 * B_YSIG, 1);
    mbar_init(bars + 8 * B_YFULL, 1);
    mbar_init(bars + 8 * B_EPOCH, 1);
    mbar_init(bars + 8 * B_PREP, 4);
    mbar_init(bars + 8 * B_USIG, 1);
    mbar_init(bars + 8 * B_WST, 1);
#pragma unroll
    for (int i = 3; i < 5; i++) mbar_init(bars + 8 * (B_KV + i), 1);
    mbar_init(bars + 8 * B_E3, 8);
    mbar_init(bars + 8 * B_LAST, 1);
    mbar_init(bars + 8 * B_OSIG, 1);
    mbar_init(bars + 8 * B_WOP, 1);
    fence_async_smem();
  }
  const int warp = __shfl_sync(0xffffffffu, tid >> 5, 0), wg = warp >> 2, w = warp & 3;
  __syncthreads();

  if (wg == 3) {
    asm volatile("setmaxnreg.dec.sync.aligned.u32 56;");
    if (w == 0) {
      if (lane == 0) {
#pragma unroll 1
        for (int kb = 1 + PRE2; kb < 10; kb++) {
          if (kb >= 4) mbar_wait(bars + 8 * (kb == 7 ? B_E3 : B_EMPTY1 + (kb & 3)), (kb >> 3) & 1);
          TSIF(kb >= 4, 44 + kb);
          load_stage(sb, kb, b, m);
          TSIF(kb == 3, 60);
          if (kb == TRIG_KB) mbar_arrive(bars + 8 * B_LAST);
        }
        mbar_wait(bars + 8 * B_WOP, 0);
        mbar_wait(bars + 8 * WL_TRIG, 0);
        mbar_wait(bars + 8 * B_EPOCH, 0);
        flag_wait(g_cnt + C_W + 32 * hg, (lds32(sb + OFF_EPOCH) + 1) * 16);
        TS(30);
#pragma unroll 1
        for (int j = 0; j < 8; j++) {
          if (j >= 6) mbar_wait(bars + 8 * (B_EMPTY2 + j - 6), 0);
          if (j == 4) mbar_wait(bars + 8 * B_ATTN, 0);
          TSIF(j >= 6, 100 + j);
          if (RF_GATE && j == 6) mbar_wait(bars + 8 * B_YSIG, 0);
          mbar_expect_tx(bars + 8 * (B_FULL2 + j), j == 0 ? WO_BYTES : j == 5 ? O_BYTES + WO_BYTES + 512 : O_BYTES + WO_BYTES);
          bulk_load(sb + off_w(j), g_WO + (hg * 8 + step_src(hg, j)) * 800, WO_BYTES, bars + 8 * (B_FULL2 + j));
        }
        mbar_wait(bars + 8 * (B_EMPTY2 + 3), 0);
        mbar_expect_tx(bars + 8 * B_QF, O_BYTES);
        tma_2d(sb + OFF_QS, &m.qm, 80 * hg, 128 * r, bars + 8 * B_QF);
        tma_2d(sb + OFF_QT, &m.qt, 80 * hg + 64, 128 * r, bars + 8 * B_QF);
      }
    } else if (w == 1) {
      unsigned epoch = 0;
      if (lane == 0) {
        epoch = atomicAdd(g_cnt + C_LAUNCH, 1u) / NCTA;
        asm volatile("st.shared.u32 [%0], %1;" ::"r"(sb + OFF_EPOCH), "r"(epoch) : "memory");
        mbar_arrive(bars + 8 * B_EPOCH);
        mbar_wait(bars + 8 * B_KVD, 0);
        mbar_expect_tx(bars + 8 * B_HB, 5 * 4096);
#pragma unroll 1
        for (int c = 0; c < 5; c++) {
          if (c == 3) mbar_wait(bars + 8 * B_S3, 0);
          bulk_load(sb + off_ch(c) + U_BYTES, p.ssm_k + (5 * b + c) * SEQ, 4096, bars + 8 * B_HB);
        }
#pragma unroll
        for (int c = 0; c < 4; c++) mbar_expect_tx(bars + 8 * (B_U + c), c < 3 ? U_BYTES : 2 * U_BYTES);
        const uint4* usrc = g_U + 5 * b * U_PITCH;
        mbar_wait(bars + 8 * B_USIG, 0);
        flag_wait(g_cnt + C_PREP + 32 * (b & 15), (epoch + 1) * NCTA);
        TS(23);
#pragma unroll
        for (int c = 0; c < 5; c++) {
          if (c == 3) mbar_wait(bars + 8 * (B_U + 2), 0);
          bulk_load(sb + off_ch(c), usrc + c * U_PITCH, U_BYTES, bars + 8 * (B_U + (c < 3 ? c : 3)));
          TSIF(c == 0 || c == 4, 116 + (c >> 2));
        }
      }
      epoch = __shfl_sync(0xffffffffu, epoch, 0);
      if (lane < 8) {
        const int src = (b & ~7) | step_src(hg, lane);
        mbar_wait(bars + 8 * B_OSIG, 0);
        TS(20);
        flag_wait(g_cnt + C_O + 32 * src, epoch + 1);
        if (lane >= 1 && lane < 4) bulk_load(sb + off_o(lane), g_O + src * 1280, O_BYTES, bars + 8 * (B_FULL2 + lane));
        __syncwarp(0xff);
        TS(21);
        if (lane == 5) bulk_load(sb + OFF_GATE, g_gate + 128 * r, 512, bars + 8 * (B_FULL2 + 5));
#pragma unroll 1
        for (int j = 4; j < 8; j++) {
          if (lane == j) {
            mbar_wait(bars + 8 * (j < 6 ? B_C34 : B_EMPTY2 + j - 6), 0);
            if (RF_GATE && j == 6) mbar_wait(bars + 8 * B_YSIG, 0);
            bulk_load(sb + off_o(j), g_O + src * 1280, O_BYTES, bars + 8 * (B_FULL2 + j));
          }
          __syncwarp(0xff);
        }
        TS(22);
      }
    } else if (w == 2) {
      mbar_wait(bars + 8 * B_PREP, 0);
      flag_signal(g_cnt + C_PREP, 16, lane);
      TS(25);
      if (lane == 0) mbar_arrive(bars + 8 * B_USIG);
      mbar_wait(bars + 8 * B_GATE, 0);
      if ((NOMB & 1) && lane == 0) asm volatile("fence.release.gpu;" ::: "memory");
      mbar_wait(bars + 8 * B_ATTN, 0);
      if (lane == 0) {
        if (O_DEFER) mbar_wait(bars + 8 * (B_U + 3), 0);
        asm volatile("cp.async.bulk.global.shared::cta.bulk_group [%0], [%1], 20480;\ncp.async.bulk.commit_group;\n"
                     "cp.async.bulk.wait_group 0;\nfence.proxy.async.global;" ::"l"(g_O + b * 1280), "r"(sb + OFF_OA) : "memory");
      }
      TS(74);
      if (!(NOMB & 1)) flag_signal(g_cnt + C_O + 32 * b, 1, lane);
      else if (lane == 0) flag_bump(g_cnt + C_O + 32 * b);
      TS(26);
      if (lane == 0) mbar_arrive(bars + 8 * B_OSIG);

    } else {
      if (lane == 0) {
        uint4* dst = g_WO + (hg * 8 + (r >> 1)) * 800 + (r & 1) * 80;
        mbar_wait(bars + 8 * B_P1, 0);
        if (!(SKIP & 2)) {
        mbar_wait(bars + 8 * WB_TRIG, 0);
        mbar_expect_tx(bars + 8 * B_WST, WO_BYTES / 2);
        tma_3d(sb + OFF_WS, &m.wo, 0, 40 * r, 5 * hg, bars + 8 * B_WST);
        mbar_wait(bars + 8 * B_WST, 0);
        mbar_wait(bars + 8 * WO_TRIG, 0);
#pragma unroll 1
        for (int n = 0; n < 5; n++)
          asm volatile("cp.async.bulk.global.shared::cta.bulk_group [%0], [%1], 1280;" ::"l"(dst + 160 * n), "r"(sb + OFF_WS + 1280 * n) : "memory");
        asm volatile("cp.async.bulk.commit_group;\ncp.async.bulk.wait_group 0;\nfence.proxy.async.global;" ::: "memory");
        if (!(NOMB & 4)) asm volatile("fence.release.gpu;" ::: "memory");
        }
        flag_bump(g_cnt + C_W + 32 * hg);
        mbar_arrive(bars + 8 * B_WOP);
        TS(71);
#pragma unroll 1
        for (int c = 0; c < 5; c++) {
          mbar_wait(bars + 8 * (B_YST + c), 0);
          asm volatile("cp.async.bulk.global.shared::cta.bulk_group [%0], [%1], 4096;\ncp.async.bulk.commit_group;"
                       ::"l"(g_Y + (5 * b + c) * Y_PITCH), "r"(sb + off_ch(c)) : "memory");
          if (c == 2) {
            asm volatile("cp.async.bulk.wait_group.read 0;" ::: "memory");
            mbar_arrive(bars + 8 * B_C34);
          }
        }
        asm volatile("cp.async.bulk.wait_group 0;\nfence.proxy.async.global;" ::: "memory");
        TS(75);
        if (!(NOMB & 2)) asm volatile("fence.release.gpu;" ::: "memory");
        flag_bump(g_cnt + C_Y + 32 * (b >> 4));
        TS(27);
        mbar_arrive(bars + 8 * B_YSIG);
        mbar_expect_tx(bars + 8 * B_YFULL, 20480);
        flag_wait(g_cnt + C_Y + 32 * hg, (lds32(sb + OFF_EPOCH) + 1) * 16);
        TS(24);
        tma_2d(sb + OFF_YT, &m.y, 128 * r, 80 * hg, bars + 8 * B_YFULL);
        tma_2d(sb + OFF_YT + 10240, &m.y, 128 * r + 64, 80 * hg, bars + 8 * B_YFULL);
      }
    }
  } else {
    asm volatile("setmaxnreg.inc.sync.aligned.u32 152;");
    if (wg < 2) {
      float acc[120];
#pragma unroll
      for (int i = 0; i < 120; i++) acc[i] = 0.f;
      const uint32_t da = desc_lo(sb + wg * 8192, 16), db = desc_lo(sb + ST_W, 8192), dc = desc_lo(sb + ST_WT, 2048);
      if (PW1) pin<120>(acc);
      if (PW1 == 2) mbar_wait(bars + 8 * B_FULL1, 0);
#pragma unroll 1
      for (int kb = 0; kb < 10; kb++) {
        mbar_wait(bars + 8 * (B_FULL1 + (kb & 3)), (kb >> 2) & 1);
        const uint32_t so = (kb & 3) * (STAGE_BYTES >> 4);
        wg_fence();
#pragma unroll
        for (int k = 0; k < 4; k++) {
          WgSST<192>::mma<HI_SW128, HI_SW128>(acc, da + so + 2 * k, db + so + 128 * k, 1);
          WgSST<48>::mma<HI_SW128, HI_SW32>(acc + 96, da + so + 2 * k, dc + so + 32 * k, 1);
        }
        wg_commit();
        wg_wait<1>();
        if (kb > 0 && lane == 0) mbar_arrive(bars + 8 * (kb == 4 ? B_E3 : B_EMPTY1 + ((kb - 1) & 3)));
      }
      mbar_wait(bars + 8 * B_EPOCH, 0);
      const uint32_t tag = lds32(sb + OFF_EPOCH) + 1;
      mbar_wait(bars + 8 * B_S3, 0);
      wg_wait<0>();
      pin<120>(acc);
      if (lane == 0) mbar_arrive(bars + 8 * B_P1);
      TSM(w == 0, 3 + wg);
      attention(acc, sb, b, wg, w, lane, tag);
    } else {
      const int tw = tid & 127, chl = 64 * (b & 1) + 8 * w + (lane >> 2);
      uint4* up = g_U + chl * U_PITCH + ((4 * (b >> 1) + (lane & 3)) ^ ((b >> 2) & 1));
      uint2 sw[10];
      uint32_t dv = 0;
      if (lane < 5) dv = __ldg(reinterpret_cast<const unsigned short*>(p.ssm_D) + 5 * b + lane);
#pragma unroll
      for (int i = 0; i < 10; i++) sw[i] = ldg64(reinterpret_cast<const uint2*>(p.shift_k) + chl + 128 * (i >> 1) + 32 * (i & 1));
      uint32_t tab[12];
      float tt[4];
      fft_tables(tab, tw);
      fft_twiddles(tt, tw);
      uint4 res[10];
#pragma unroll
      for (int i = 0; i < 10; i++) res[i] = make_uint4(0, 0, 0, 0);
#pragma unroll 1
      for (int slab = 0; slab < 5; slab++) {
#pragma unroll
        for (int i = 0; i < 8; i++) res[i] = res[i + 2];
        prep_slab(res + 8, sw, sb, slab, w, lane);
        TSIF(w == 0, 99 + 4 * slab);
#pragma unroll
        for (int i = 0; i < 8; i++) sw[i] = sw[i + 2];
      }
      TSIF(w == 0, 28);
      __syncwarp();
      if (lane == 0) mbar_arrive(bars + 8 * B_KVD + ((res[8].x ^ res[9].x) & p.zero));
      mbar_wait(bars + 8 * B_KVD, 0);
      fft_tables_store(tab, sb, tw);
      mbar_wait(bars + 8 * B_LAST, 0);
#pragma unroll
      for (int i = 0; i < 10; i++) up[(128 * (i >> 1) + 32 * (i & 1)) * U_PITCH] = res[i];
      __syncwarp();
      if (lane == 0) mbar_arrive(bars + 8 * B_PREP);
      TSIF(w == 0 && !U_TMA, 5);
      mbar_wait(bars + 8 * (G_AFTER ? B_USIG : B_LAST), 0);
      if (!(SKIP & 1)) prep_gate(p, b, w, lane);
      __syncwarp();
      if (lane == 0) mbar_arrive(bars + 8 * B_GATE);
      TSIF(w == 0, 72);
      mbar_wait(bars + 8 * B_HB, 0);
      TSIF(w == 0, 2);
      const uint32_t ha = sb + U_BYTES + ((tw >> 3) * 16 + 8 + (tw & 7)) * 16;
      uint4 hv[5];
#pragma unroll
      for (int c = 0; c < 5; c++) hv[c] = lds128(ha + off_ch(c));
      __syncwarp();
#pragma unroll
      for (int c = 0; c < 5; c++) sts128((ha ^ 16) + off_ch(c), hv[c].x, hv[c].y, hv[c].z, hv[c].w);
      sts128(sb + OFF_TT + 16 * tw, __float_as_uint(tt[0]), __float_as_uint(tt[1]), __float_as_uint(tt[2]), __float_as_uint(tt[3]));
      if (tw < 5) asm volatile("st.shared.f32 [%0], %1;" ::"r"(sb + OFF_D + 4 * tw), "f"(bf_lo(dv) * 0.125f) : "memory");
      fence_async_smem();
      __syncwarp();
      if (lane == 0) mbar_arrive(bars + 8 * B_HA);
      TSIF(w == 0, 6);
    }

    FftConst fc;
    TSM(w == 0 && wg == 0, 104);
    mbar_wait(bars + 8 * B_HA, 0);
    fft_matrices(fc, sb, w, lane);
    TSM(w == 0 && wg == 0, 105);
    if (ATT_GATE && !H_EARLY) mbar_wait(bars + 8 * B_ATTN, 0);
    TSM(w == 0 && wg == 2, 124);
#pragma unroll 1
    for (uint32_t tasks = wg == 0 ? TASK0 : wg == 1 ? TASK1 : TASK2; tasks; tasks >>= 4) {
      const int c = (tasks & 7) - 1;
      conv_channel(fc, sb, c, wg, w, lane);
      if (lane == 0) mbar_arrive(bars + 8 * (B_YST + c));
      TSM(w == 0, 10 + c);
    }

    if (wg < 2) {
      const int g = lane >> 2;
      float acc[40];
#pragma unroll
      for (int i = 0; i < 40; i++) acc[i] = 0.f;
      const uint32_t da = desc_lo(sb + wg * 1024, 2048), db = desc_lo(sb, 2560);
      mbar_wait(bars + 8 * B_ATTN, 0);
      mbar_wait(bars + 8 * (B_YST + 3), 0);
      mbar_wait(bars + 8 * (B_YST + 4), 0);
      if (PW2) mbar_wait(bars + 8 * B_FULL2, 0);
      TSM(w == 0, 15 + wg);
#pragma unroll 1
      for (int j = 0; j < 8; j++) {
        mbar_wait(bars + 8 * (B_FULL2 + j), 0);
        const uint32_t oa = da + (off_o(j) >> 4), ob = db + (off_w(j) >> 4);
        wg_fence();
#pragma unroll
        for (int k = 0; k < 5; k++) WgSST<80>::mma<HI_NONE, HI_SW32>(acc, oa + 256 * k, ob + 32 * k, 1);
        wg_commit();
        wg_wait<1>();
        if (j >= 1 && j <= 4 && lane == 0) mbar_arrive(bars + 8 * (B_EMPTY2 + j - 1));
      }
      TSIF(w == 0 && wg == 0, 113);
      const int tr = 64 * wg + 16 * w + (lane & 15);
      const uint32_t fm = sb + OFF_QS + tr * 128, fx = (lane >> 4) ^ (tr & 7);
      const uint32_t ft = sb + OFF_QT + tr * 32 + (((lane >> 4) ^ (tr >> 2)) & 1) * 16;
      const float g0 = __uint_as_float(lds32(sb + OFF_GATE + (64 * wg + 16 * w + g) * 4));
      const float g1 = __uint_as_float(lds32(sb + OFF_GATE + (64 * wg + 16 * w + 8 + g) * 4));
      const uint32_t ga = pack2(g0, g0), gb = pack2(g1, g1);
      const uint32_t na = pack2(1.f - g0, 1.f - g0), nb = pack2(1.f - g1, 1.f - g1);

      wg_wait<0>();
      pin<40>(acc);
      TSM(w == 0, 17 + wg);
      uint32_t pb[20];
#pragma unroll
      for (int j = 0; j < 10; j++) {
        pb[2 * j] = bmul(na, pack2(acc[4 * j], acc[4 * j + 1]));
        pb[2 * j + 1] = bmul(nb, pack2(acc[4 * j + 2], acc[4 * j + 3]));
        asm volatile("" : "+r"(pb[2 * j]), "+r"(pb[2 * j + 1]));
      }
      const uint32_t ya = sb + OFF_YT + wg * 10240 + ((lane >> 4) * 8 + (lane & 7)) * 128 +
                          (((2 * w + (((lane >> 3) & 1) ^ wg)) ^ (lane & 7)) << 4);
      uint32_t qf[20];
      mbar_wait(bars + 8 * B_QF, 0);
#pragma unroll
      for (int j = 0; j < 5; j++) ldsm4(qf + 4 * j, j < 4 ? fm + ((fx ^ (2 * j)) << 4) : ft);
      mbar_wait(bars + 8 * B_YFULL, 0);
      TSM(w == 0 && wg == 0, 19);
#pragma unroll
      for (int j = 0; j < 5; j++) {
        uint32_t y[4];
        ldsm4t(y, ya + 2048 * j);
#pragma unroll
        for (int i = 0; i < 4; i++) qf[4 * j + i] = badd(bmul((i & 1) ? gb : ga, bmul(qf[4 * j + i], y[i])), pb[4 * j + i]);
      }
#pragma unroll
      for (int j = 0; j < 5; j++) stsm4(j < 4 ? fm + ((fx ^ (2 * j)) << 4) : ft, qf + 4 * j);
      fence_async_smem();
      __syncwarp();
      if (lane == 0) {
        const int row = 64 * wg + 16 * w;
        asm volatile("cp.async.bulk.tensor.2d.global.shared::cta.bulk_group [%0, {%2, %3}], [%1];"
                     ::"l"(&m.om), "r"(sb + OFF_QS + row * 128), "r"(80 * hg), "r"(128 * r + row) : "memory");
        asm volatile("cp.async.bulk.tensor.2d.global.shared::cta.bulk_group [%0, {%2, %3}], [%1];"
                     ::"l"(&m.ot), "r"(sb + OFF_QT + row * 32), "r"(80 * hg + 64), "r"(128 * r + row) : "memory");
        asm volatile("cp.async.bulk.commit_group;\ncp.async.bulk.wait_group.read 0;" ::: "memory");
      }
      TSM(true, 40 + 4 * wg + w);
      if (ENDBAR) asm volatile("bar.sync 15, 256;" ::: "memory");
    }
  }
}

typedef CUresult (*EncodeFn)(CUtensorMap*, CUtensorMapDataType, cuuint32_t, void*, const cuuint64_t*, const cuuint64_t*,
                             const cuuint32_t*, const cuuint32_t*, CUtensorMapInterleave, CUtensorMapSwizzle,
                             CUtensorMapL2promotion, CUtensorMapFloatOOBfill);

void encode(EncodeFn fn, CUtensorMap* tm, const void* base, int rank, const cuuint64_t* dims, const cuuint64_t* strides,
            const cuuint32_t* box, CUtensorMapSwizzle swz) {
  const cuuint32_t ones[3] = {1, 1, 1};
  fn(tm, CU_TENSOR_MAP_DATA_TYPE_BFLOAT16, rank, const_cast<void*>(base), dims, strides, box, ones,
     CU_TENSOR_MAP_INTERLEAVE_NONE, swz, CU_TENSOR_MAP_L2_PROMOTION_L2_128B, CU_TENSOR_MAP_FLOAT_OOB_FILL_NONE);
}

}

extern "C" void kernel_launch(void* const* d_in, const int* in_sizes, int n_in, void* d_out, int out_size) {
  (void)in_sizes; (void)n_in; (void)out_size;
  Params p;
  p.q = (const __nv_bfloat16*)d_in[0];
  p.k = (const __nv_bfloat16*)d_in[1];
  p.v = (const __nv_bfloat16*)d_in[2];
  p.shift_k = (const __nv_bfloat16*)d_in[3];
  p.ssm_k = (const __nv_bfloat16*)d_in[4];
  p.ssm_D = (const __nv_bfloat16*)d_in[5];
  p.wqkv = (const __nv_bfloat16*)d_in[7];
  p.wo = (const __nv_bfloat16*)d_in[8];
  p.gate_w = (const __nv_bfloat16*)d_in[9];
  p.out = (__nv_bfloat16*)d_out;
  p.zero = 0;

  static EncodeFn fn = nullptr;
  static void *yaddr = nullptr, *uaddr = nullptr;
  if (!fn) {
    cudaDriverEntryPointQueryResult qr;
    void* f = nullptr;
    cudaGetDriverEntryPoint("cuTensorMapEncodeTiled", &f, cudaEnableDefault, &qr);
    fn = (EncodeFn)f;
    cudaGetSymbolAddress(&yaddr, g_Y);
    cudaGetSymbolAddress(&uaddr, g_U);
    cudaFuncSetAttribute(fused_kernel, cudaFuncAttributeMaxDynamicSharedMemorySize, SMEM_BYTES);
  }
  Maps m;
  {
    const cuuint64_t dims[3] = {640, 1024, 2}, st[2] = {2560, 1280};
    const cuuint32_t box[3] = {64, 64, 2};
    encode(fn, &m.x, p.q, 3, dims, st, box, CU_TENSOR_MAP_SWIZZLE_128B);
  }
  {
    const cuuint64_t dims[3] = {640, 640, 3}, st[2] = {3840, 1280};
    const cuuint32_t box[3] = {64, 64, 3}, boxt[3] = {16, 64, 3};
    encode(fn, &m.wm, p.wqkv, 3, dims, st, box, CU_TENSOR_MAP_SWIZZLE_128B);
    encode(fn, &m.wt, p.wqkv, 3, dims, st, boxt, CU_TENSOR_MAP_SWIZZLE_32B);
  }
  {
    const cuuint64_t dims[3] = {64, 2048, 10}, st[2] = {1280, 128};
    const cuuint32_t boxk[3] = {64, 35, 1}, boxv[3] = {64, 32, 1};
    encode(fn, &m.k, p.k, 3, dims, st, boxk, CU_TENSOR_MAP_SWIZZLE_128B);
    encode(fn, &m.v, p.v, 3, dims, st, boxv, CU_TENSOR_MAP_SWIZZLE_128B);
  }
  {
    const cuuint64_t dims[3] = {16, 640, 40}, st[2] = {1280, 32};
    const cuuint32_t box[3] = {16, 40, 5};
    encode(fn, &m.wo, p.wo, 3, dims, st, box, CU_TENSOR_MAP_SWIZZLE_32B);
  }
  {
    const cuuint64_t dims[2] = {2048, 640}, st[1] = {Y_PITCH * 16};
    const cuuint32_t box[2] = {64, 80};
    encode(fn, &m.y, yaddr, 2, dims, st, box, CU_TENSOR_MAP_SWIZZLE_128B);
    const cuuint64_t stu[1] = {U_PITCH * 16};
    const cuuint32_t boxu[2] = {32, 64};
    encode(fn, &m.u, uaddr, 2, dims, stu, boxu, CU_TENSOR_MAP_SWIZZLE_NONE);
  }
  {
    const cuuint64_t dims[2] = {640, 2048}, st[1] = {1280};
    const cuuint32_t bqm[2] = {64, 128}, bqt[2] = {16, 128}, bom[2] = {64, 16}, bot[2] = {16, 16};
    encode(fn, &m.qm, p.q, 2, dims, st, bqm, CU_TENSOR_MAP_SWIZZLE_128B);
    encode(fn, &m.qt, p.q, 2, dims, st, bqt, CU_TENSOR_MAP_SWIZZLE_32B);
    encode(fn, &m.om, p.out, 2, dims, st, bom, CU_TENSOR_MAP_SWIZZLE_128B);
    encode(fn, &m.ot, p.out, 2, dims, st, bot, CU_TENSOR_MAP_SWIZZLE_32B);
  }
  fused_kernel<<<NCTA, NTHR, SMEM_BYTES>>>(m, p);
}
```

```cpp
#include <cuda.h>
#include <cuda_bf16.h>
#include <cuda_runtime.h>
#include <stdint.h>

namespace {

constexpr int SEQ = 2048, DIM = 640, NCTA = 128, NHELP = 4, NTHR = 512;

#define TRIG_KB 9
#define KV_KB 2
#define DEV_EXIT 0
#define ATT_GATE 1
#define FENCE_LO 0
#define FENCE_HI 0
#define PW1 2
#define PW2 1
#define ENDBAR 0
#define PAD_KB 0
#define Y_ALIAS 1
#define H_EARLY 1
#define NOMB 0
#define SRC_ROT 0
#define WAIT_NS 0
#define TAILF 1
#define T_ISSUE 384
#define T_PF 416
#define T_INIT 448
#define ATT_MERGE 0
#define BMAP 1
#define PRE2 1
#define KV_MIX 0
#define O_DEFER 0
#define TASK0 0x52
#define TASK1 0x3
#define TASK2 0x41
#define HALO_FIRST 1
#define PREV_EARLY 0
#define ACQ 0
#define U_TMA 0
#define U_GATE 0
#define RF_GATE 0
#define WL_TRIG B_U
#define WO_GATE 1

constexpr uint32_t STAGE_BYTES = 47104, ST_W = 16384, ST_WT = 40960;
constexpr uint32_t O_BYTES = 20480, WO_BYTES = 12800;
constexpr uint32_t OFF_OA = 0;
constexpr uint32_t OFF_QS = 3 * O_BYTES, OFF_QT = OFF_QS + 16384;
constexpr uint32_t OFF_WC = 81920;
constexpr uint32_t OFF_WA = 94720;
constexpr uint32_t OFF_GATE = 145920;
constexpr uint32_t OFF_TT = 146432;
constexpr uint32_t OFF_KVX = 148480;
constexpr uint32_t OFF_CH3 = 163840;
constexpr uint32_t CH_BYTES = 12288, U_BYTES = 4096;
constexpr uint32_t OFF_FT = 225280, OFF_GT = 229376;
constexpr uint32_t OFF_CH0 = 188416;
constexpr uint32_t OFF_KVS = OFF_CH0, KVS_V = 4480, KVS_BYTES = 8576;
__device__ __forceinline__ uint32_t off_us(int s) { return OFF_CH0 + 4096 * ((0x65320 >> (4 * s)) & 7); }
constexpr uint32_t OFF_YT = 163840;
constexpr uint32_t OFF_BAR = 231936;
constexpr uint32_t SMEM_BYTES = OFF_BAR + 512;

enum : uint32_t {
  B_FULL1 = 0, B_EMPTY1 = 4, B_S3 = 7, B_FULL2 = 52, B_EMPTY2 = 13, B_U = 8, B_GATE = 12, B_HA = 19, B_HB = 20,
  B_ATTN = 21, B_C34 = 22, B_CONV = 23, B_YFULL = 24, B_EPOCH = 25, B_PREP = 26, B_P1 = 27, B_LAST = 28,
  B_E3 = 29, B_OSIG = 30, B_WOP = 31, B_USIG = 32, B_WST = 33, B_KV = 34, B_KVD = 39, B_QF = 17, B_YST = 40,
  B_US = 45, B_YSIG = 50
};
constexpr uint32_t OFF_EPOCH = OFF_BAR + 8 * 51, OFF_D = OFF_BAR + 8 * 60;
__device__ __forceinline__ uint32_t off_o(int j) { return j < 4 ? OFF_OA + j * O_BYTES : j < 6 ? OFF_CH0 + (j - 4) * O_BYTES : OFF_OA + (j - 6) * O_BYTES; }
__device__ __forceinline__ uint32_t off_w(int j) { return j < 4 ? OFF_WA + j * WO_BYTES : j == 4 ? OFF_KVX : j == 5 ? OFF_WC : OFF_WA + (j - 6) * WO_BYTES; }
__device__ __forceinline__ int step_src(int hg, int j) { return SRC_ROT ? (hg + j) & 7 : j == 0 ? hg : j <= hg ? j - 1 : j; }
__device__ __forceinline__ bool tail_first(int hg) { return TAILF && (hg & 3) == 3; }
__device__ __forceinline__ uint32_t off_ch(int c) { return (c < 3 ? OFF_CH0 : OFF_CH3 - 3 * CH_BYTES) + c * CH_BYTES; }

#define U_PITCH 264
__device__ __align__(1024) uint4 g_U[DIM * U_PITCH];
__device__ uint4 g_O[NCTA * 1280];
#define g_Y g_U
constexpr int Y_PITCH = U_PITCH;
__device__ uint4 g_WO[64 * 800];
__device__ uint4 g_halo[NCTA * 2 * 7 * 32];
__device__ float g_gate[SEQ + PAD_KB * 256];
__device__ unsigned g_cnt[32 * (1 + 2 * 16 + 8 + NCTA)];
constexpr int C_LAUNCH = 0, C_PREP = 32, C_Y = 32 * 17, C_G = 32 * 25, C_W = 32 * 33, C_O = 32 * 41;

#define TSM(cond, slot) do { } while (0)
#define TSIF(cond, slot) do { if (__LINE__ >= FENCE_LO && __LINE__ < FENCE_HI) sched_fence(); } while (0)
__device__ __forceinline__ void sched_fence() {
  asm volatile("{\n.reg .pred p;\n.reg .u32 c;\nmov.u32 c, %%clock;\nsetp.eq.u32 p, c, 0;\n@p st.shared.u32 [%0], c;\n}"
               ::"r"(1024 + OFF_EPOCH + 4) : "memory");
}
#define TS(slot) TSIF(true, slot)

struct Params {
  const __nv_bfloat16 *q, *k, *v, *shift_k, *ssm_k, *ssm_D, *wqkv, *wo, *gate_w;
  __nv_bfloat16* out;
  uint32_t zero;
};

#define POLL_NS 0
constexpr int SPIN_LIMIT = 1 << 17;

__device__ __forceinline__ void mbar_init(uint32_t bar, uint32_t count) {
  asm volatile("mbarrier.init.shared::cta.b64 [%0], %1;" ::"r"(bar), "r"(count) : "memory");
}
__device__ __forceinline__ void mbar_expect_tx(uint32_t bar, uint32_t bytes) {
  asm volatile("mbarrier.arrive.expect_tx.shared::cta.b64 _, [%0], %1;" ::"r"(bar), "r"(bytes) : "memory");
}
__device__ __forceinline__ void mbar_arrive(uint32_t bar) {
  asm volatile("mbarrier.arrive.shared::cta.b64 _, [%0];" ::"r"(bar) : "memory");
}
__device__ __forceinline__ void mbar_wait(uint32_t bar, uint32_t parity) {
  uint32_t ok;
  int spins = 0;
  do {
    if (WAIT_NS)
      asm volatile("{\n.reg .pred p;\nmbarrier.try_wait.parity.shared::cta.b64 p, [%1], %2, %3;\nselp.b32 %0, 1, 0, p;\n}"
                   : "=r"(ok) : "r"(bar), "r"(parity), "r"(WAIT_NS) : "memory");
    else
      asm volatile("{\n.reg .pred p;\nmbarrier.try_wait.parity.shared::cta.b64 p, [%1], %2;\nselp.b32 %0, 1, 0, p;\n}"
                   : "=r"(ok) : "r"(bar), "r"(parity) : "memory");
    if (++spins > SPIN_LIMIT) break;
  } while (!ok);
}
__device__ __forceinline__ unsigned flag_read(const unsigned* p) {
  unsigned v;
  asm volatile("ld.relaxed.gpu.global.u32 %0, [%1];" : "=r"(v) : "l"(p) : "memory");
  return v;
}
__device__ __forceinline__ void flag_poll(const unsigned* p, unsigned target) {
  unsigned v;
  int spins = 0;
  do {
    if (POLL_NS && spins) __nanosleep(POLL_NS);
    asm volatile("ld.relaxed.gpu.global.u32 %0, [%1];" : "=r"(v) : "l"(p) : "memory");
    if (++spins > SPIN_LIMIT) break;
  } while ((int)(v - target) < 0);
}
__device__ __forceinline__ void flag_wait(const unsigned* p, unsigned target) {
  flag_poll(p, target);
  if (ACQ) asm volatile("fence.acquire.gpu;\nfence.proxy.async.global;" ::: "memory");
}
__device__ __forceinline__ void flag_signal(unsigned* p, int n, int lane) {
  if (lane == 0) asm volatile("fence.release.gpu;" ::: "memory");
  __syncwarp();
  if (lane < n) asm volatile("red.relaxed.gpu.global.add.u32 [%0], 1;" ::"l"(p + 32 * lane) : "memory");
}
__device__ __forceinline__ void flag_bump(unsigned* p) {
  asm volatile("red.relaxed.gpu.global.add.u32 [%0], 1;" ::"l"(p) : "memory");
}
__device__ __forceinline__ void fence_async_smem() { asm volatile("fence.proxy.async.shared::cta;" ::: "memory"); }
__device__ __forceinline__ void wg_sync(int id) { asm volatile("bar.sync %0, 128;" ::"r"(id) : "memory"); }

__device__ __forceinline__ void tma_2d(uint32_t dst, const CUtensorMap* tm, int c0, int c1, uint32_t bar) {
  asm volatile("cp.async.bulk.tensor.2d.shared::cluster.global.mbarrier::complete_tx::bytes [%0], [%1, {%3, %4}], [%2];"
               ::"r"(dst), "l"(tm), "r"(bar), "r"(c0), "r"(c1) : "memory");
}
__device__ __forceinline__ void tma_3d(uint32_t dst, const CUtensorMap* tm, int c0, int c1, int c2, uint32_t bar) {
  asm volatile("cp.async.bulk.tensor.3d.shared::cluster.global.mbarrier::complete_tx::bytes [%0], [%1, {%3, %4, %5}], [%2];"
               ::"r"(dst), "l"(tm), "r"(bar), "r"(c0), "r"(c1), "r"(c2) : "memory");
}
__device__ __forceinline__ void bulk_load(uint32_t dst, const void* src, uint32_t bytes, uint32_t bar) {
  asm volatile("cp.async.bulk.shared::cluster.global.mbarrier::complete_tx::bytes [%0], [%1], %2, [%3];"
               ::"r"(dst), "l"(src), "r"(bytes), "r"(bar) : "memory");
}
__device__ __forceinline__ void tm_prefetch(const CUtensorMap* tm) {
  asm volatile("prefetch.tensormap [%0];" ::"l"(tm) : "memory");
}

__device__ __forceinline__ void wg_fence() { asm volatile("wgmma.fence.sync.aligned;" ::: "memory"); }
__device__ __forceinline__ void wg_commit() { asm volatile("wgmma.commit_group.sync.aligned;" ::: "memory"); }
template <int N> __device__ __forceinline__ void wg_wait() { asm volatile("wgmma.wait_group.sync.aligned %0;" ::"n"(N) : "memory"); }
__device__ __forceinline__ uint32_t desc_lo(uint32_t addr, uint32_t lbo) { return ((addr & 0x3FFFF) >> 4) | ((lbo >> 4) << 16); }
constexpr uint32_t desc_hi(uint32_t sbo, uint32_t swz) { return (sbo >> 4) | (swz << 30); }
constexpr uint32_t HI_SW128 = desc_hi(1024, 1), HI_SW64 = desc_hi(512, 2), HI_SW32 = desc_hi(256, 3), HI_NONE = desc_hi(128, 0);
template <int N> __device__ __forceinline__ void pin(float* d) {
#pragma unroll
  for (int i = 0; i < N; i++) asm volatile("" : "+f"(d[i])::"memory");
}

__device__ __forceinline__ uint32_t lds32(uint32_t a) {
  uint32_t v;
  asm volatile("ld.volatile.shared.u32 %0, [%1];" : "=r"(v) : "r"(a) : "memory");
  return v;
}
__device__ __forceinline__ uint4 ldg128(const void* a) {
  uint4 v;
  asm volatile("ld.global.nc.v4.u32 {%0, %1, %2, %3}, [%4];" : "=r"(v.x), "=r"(v.y), "=r"(v.z), "=r"(v.w) : "l"(a) : "memory");
  return v;
}
__device__ __forceinline__ uint2 ldg64(const void* a) {
  uint2 v;
  asm volatile("ld.global.nc.v2.u32 {%0, %1}, [%2];" : "=r"(v.x), "=r"(v.y) : "l"(a) : "memory");
  return v;
}
__device__ __forceinline__ void ldsm4(uint32_t* r, uint32_t a) {
  asm volatile("ldmatrix.sync.aligned.m8n8.x4.shared.b16 {%0, %1, %2, %3}, [%4];"
               : "=r"(r[0]), "=r"(r[1]), "=r"(r[2]), "=r"(r[3]) : "r"(a) : "memory");
}
__device__ __forceinline__ void ldsm4t(uint32_t* r, uint32_t a) {
  asm volatile("ldmatrix.sync.aligned.m8n8.x4.trans.shared.b16 {%0, %1, %2, %3}, [%4];"
               : "=r"(r[0]), "=r"(r[1]), "=r"(r[2]), "=r"(r[3]) : "r"(a) : "memory");
}
__device__ __forceinline__ uint4 lds128(uint32_t a) {
  uint4 v;
  asm volatile("ld.shared.v4.u32 {%0, %1, %2, %3}, [%4];" : "=r"(v.x), "=r"(v.y), "=r"(v.z), "=r"(v.w) : "r"(a) : "memory");
  return v;
}
__device__ __forceinline__ void sts128(uint32_t a, uint32_t x, uint32_t y, uint32_t z, uint32_t w) {
  asm volatile("st.shared.v4.u32 [%0], {%1, %2, %3, %4};" ::"r"(a), "r"(x), "r"(y), "r"(z), "r"(w) : "memory");
}
__device__ __forceinline__ void stsm4(uint32_t a, const uint32_t* r) {
  asm volatile("stmatrix.sync.aligned.m8n8.x4.shared.b16 [%0], {%1, %2, %3, %4};" ::"r"(a), "r"(r[0]), "r"(r[1]), "r"(r[2]), "r"(r[3]) : "memory");
}
__device__ __forceinline__ void stsm4t(uint32_t a, const uint32_t* r) {
  asm volatile("stmatrix.sync.aligned.m8n8.x4.trans.shared.b16 [%0], {%1, %2, %3, %4};" ::"r"(a), "r"(r[0]), "r"(r[1]), "r"(r[2]), "r"(r[3]) : "memory");
}
__device__ __forceinline__ uint32_t pack2(float lo, float hi) {
  uint32_t r;
  asm("cvt.rn.bf16x2.f32 %0, %1, %2;" : "=r"(r) : "f"(hi), "f"(lo));
  return r;
}
__device__ __forceinline__ uint32_t movm(uint32_t a) {
  uint32_t d;
  asm volatile("movmatrix.sync.aligned.m8n8.trans.b16 %0, %1;" : "=r"(d) : "r"(a));
  return d;
}
__device__ __forceinline__ uint32_t bmul(uint32_t a, uint32_t b) {
  uint32_t d;
  asm("mul.rn.bf16x2 %0, %1, %2;" : "=r"(d) : "r"(a), "r"(b));
  return d;
}
__device__ __forceinline__ uint32_t badd(uint32_t a, uint32_t b) {
  uint32_t d;
  asm("add.rn.bf16x2 %0, %1, %2;" : "=r"(d) : "r"(a), "r"(b));
  return d;
}
__device__ __forceinline__ float bf_lo(uint32_t x) { return __uint_as_float(x << 16); }
__device__ __forceinline__ float bf_hi(uint32_t x) { return __uint_as_float(x & 0xFFFF0000u); }
__device__ __forceinline__ float ex2(float x) {
  float y;
  asm("ex2.approx.ftz.f32 %0, %1;" : "=f"(y) : "f"(x));
  return y;
}
__device__ __forceinline__ float rcp(float x) {
  float y;
  asm("rcp.approx.ftz.f32 %0, %1;" : "=f"(y) : "f"(x));
  return y;
}
__device__ __forceinline__ void mma16816(float* d, uint32_t a0, uint32_t a1, uint32_t a2, uint32_t a3, uint32_t b0, uint32_t b1) {
  asm volatile("mma.sync.aligned.m16n8k16.row.col.f32.bf16.bf16.f32 {%0, %1, %2, %3}, {%4, %5, %6, %7}, {%8, %9}, {%0, %1, %2, %3};"
               : "+f"(d[0]), "+f"(d[1]), "+f"(d[2]), "+f"(d[3])
               : "r"(a0), "r"(a1), "r"(a2), "r"(a3), "r"(b0), "r"(b1));
}
__device__ __forceinline__ void mma1688(float* d, uint32_t a0, uint32_t a1, uint32_t b0) {
  asm volatile("mma.sync.aligned.m16n8k8.row.col.f32.bf16.bf16.f32 {%0, %1, %2, %3}, {%4, %5}, {%6}, {%0, %1, %2, %3};"
               : "+f"(d[0]), "+f"(d[1]), "+f"(d[2]), "+f"(d[3])
               : "r"(a0), "r"(a1), "r"(b0));
}

template <int N> struct WgRS;
template <int N> struct WgSST;
template <> struct WgRS<32> {
  template <uint32_t HB>
  static __device__ __forceinline__ void mma(float* d, const uint32_t* a, uint32_t db) {
    asm volatile("{\n.reg .pred p;\n.reg .b64 db;\nsetp.ne.b32 p, %22, 0;\n"
      "mov.b64 db, {%20, %21};\n"
      "wgmma.mma_async.sync.aligned.m64n32k16.f32.bf16.bf16 {"
      "%0, %1, %2, %3, %4, %5, %6, %7, %8, %9, %10, %11, %12, %13, %14, %15"
      "}, {%16, %17, %18, %19}, db, p, 1, 1, 1;\n}\n"
      : "+f"(d[0]), "+f"(d[1]), "+f"(d[2]), "+f"(d[3]), "+f"(d[4]), "+f"(d[5]), "+f"(d[6]), "+f"(d[7]),
        "+f"(d[8]), "+f"(d[9]), "+f"(d[10]), "+f"(d[11]), "+f"(d[12]), "+f"(d[13]), "+f"(d[14]), "+f"(d[15])
      : "r"(a[0]), "r"(a[1]), "r"(a[2]), "r"(a[3]), "r"(db), "n"(HB), "n"(1));
  }
  template <uint32_t HB>
  static __device__ __forceinline__ void set(float* d, const uint32_t* a, uint32_t db) {
    asm volatile("{\n.reg .pred p;\n.reg .b64 db;\nsetp.ne.b32 p, %22, 0;\n"
      "mov.b64 db, {%20, %21};\n"
      "wgmma.mma_async.sync.aligned.m64n32k16.f32.bf16.bf16 {"
      "%0, %1, %2, %3, %4, %5, %6, %7, %8, %9, %10, %11, %12, %13, %14, %15"
      "}, {%16, %17, %18, %19}, db, p, 1, 1, 1;\n}\n"
      : "=f"(d[0]), "=f"(d[1]), "=f"(d[2]), "=f"(d[3]), "=f"(d[4]), "=f"(d[5]), "=f"(d[6]), "=f"(d[7]),
        "=f"(d[8]), "=f"(d[9]), "=f"(d[10]), "=f"(d[11]), "=f"(d[12]), "=f"(d[13]), "=f"(d[14]), "=f"(d[15])
      : "r"(a[0]), "r"(a[1]), "r"(a[2]), "r"(a[3]), "r"(db), "n"(HB), "n"(0));
  }
};
template <> struct WgRS<64> {
  template <uint32_t HB>
  static __device__ __forceinline__ void mma(float* d, const uint32_t* a, uint32_t db) {
    asm volatile("{\n.reg .pred p;\n.reg .b64 db;\nsetp.ne.b32 p, %38, 0;\n"
      "mov.b64 db, {%36, %37};\n"
      "wgmma.mma_async.sync.aligned.m64n64k16.f32.bf16.bf16 {"
      "%0, %1, %2, %3, %4, %5, %6, %7, %8, %9, %10, %11, %12, %13, %14, %15, "
      "%16, %17, %18, %19, %20, %21, %22, %23, %24, %25, %26, %27, %28, %29, %30, %31"
      "}, {%32, %33, %34, %35}, db, p, 1, 1, 1;\n}\n"
      : "+f"(d[0]), "+f"(d[1]), "+f"(d[2]), "+f"(d[3]), "+f"(d[4]), "+f"(d[5]), "+f"(d[6]), "+f"(d[7]),
        "+f"(d[8]), "+f"(d[9]), "+f"(d[10]), "+f"(d[11]), "+f"(d[12]), "+f"(d[13]), "+f"(d[14]), "+f"(d[15]),
        "+f"(d[16]), "+f"(d[17]), "+f"(d[18]), "+f"(d[19]), "+f"(d[20]), "+f"(d[21]), "+f"(d[22]), "+f"(d[23]),
        "+f"(d[24]), "+f"(d[25]), "+f"(d[26]), "+f"(d[27]), "+f"(d[28]), "+f"(d[29]), "+f"(d[30]), "+f"(d[31])
      : "r"(a[0]), "r"(a[1]), "r"(a[2]), "r"(a[3]), "r"(db), "n"(HB), "n"(1));
  }
  template <uint32_t HB>
  static __device__ __forceinline__ void set(float* d, const uint32_t* a, uint32_t db) {
    asm volatile("{\n.reg .pred p;\n.reg .b64 db;\nsetp.ne.b32 p, %38, 0;\n"
      "mov.b64 db, {%36, %37};\n"
      "wgmma.mma_async.sync.aligned.m64n64k16.f32.bf16.bf16 {"
      "%0, %1, %2, %3, %4, %5, %6, %7, %8, %9, %10, %11, %12, %13, %14, %15, "
      "%16, %17, %18, %19, %20, %21, %22, %23, %24, %25, %26, %27, %28, %29, %30, %31"
      "}, {%32, %33, %34, %35}, db, p, 1, 1, 1;\n}\n"
      : "=f"(d[0]), "=f"(d[1]), "=f"(d[2]), "=f"(d[3]), "=f"(d[4]), "=f"(d[5]), "=f"(d[6]), "=f"(d[7]),
        "=f"(d[8]), "=f"(d[9]), "=f"(d[10]), "=f"(d[11]), "=f"(d[12]), "=f"(d[13]), "=f"(d[14]), "=f"(d[15]),
        "=f"(d[16]), "=f"(d[17]), "=f"(d[18]), "=f"(d[19]), "=f"(d[20]), "=f"(d[21]), "=f"(d[22]), "=f"(d[23]),
        "=f"(d[24]), "=f"(d[25]), "=f"(d[26]), "=f"(d[27]), "=f"(d[28]), "=f"(d[29]), "=f"(d[30]), "=f"(d[31])
      : "r"(a[0]), "r"(a[1]), "r"(a[2]), "r"(a[3]), "r"(db), "n"(HB), "n"(0));
  }
};
template <> struct WgSST<48> {
  template <uint32_t HA, uint32_t HB>
  static __device__ __forceinline__ void mma(float* d, uint32_t da, uint32_t db, int sc) {
    asm volatile("{\n.reg .pred p;\n.reg .b64 da, db;\nsetp.ne.b32 p, %28, 0;\n"
      "mov.b64 da, {%24, %25};\nmov.b64 db, {%26, %27};\n"
      "wgmma.mma_async.sync.aligned.m64n48k16.f32.bf16.bf16 {"
      "%0, %1, %2, %3, %4, %5, %6, %7, %8, %9, %10, %11, %12, %13, %14, %15, "
      "%16, %17, %18, %19, %20, %21, %22, %23"
      "}, da, db, p, 1, 1, 0, 1;\n}\n"
      : "+f"(d[0]), "+f"(d[1]), "+f"(d[2]), "+f"(d[3]), "+f"(d[4]), "+f"(d[5]), "+f"(d[6]), "+f"(d[7]),
        "+f"(d[8]), "+f"(d[9]), "+f"(d[10]), "+f"(d[11]), "+f"(d[12]), "+f"(d[13]), "+f"(d[14]), "+f"(d[15]),
        "+f"(d[16]), "+f"(d[17]), "+f"(d[18]), "+f"(d[19]), "+f"(d[20]), "+f"(d[21]), "+f"(d[22]), "+f"(d[23])
      : "r"(da), "n"(HA), "r"(db), "n"(HB), "r"(sc));
  }
};
template <> struct WgSST<80> {
  template <uint32_t HA, uint32_t HB>
  static __device__ __forceinline__ void mma(float* d, uint32_t da, uint32_t db, int sc) {
    asm volatile("{\n.reg .pred p;\n.reg .b64 da, db;\nsetp.ne.b32 p, %44, 0;\n"
      "mov.b64 da, {%40, %41};\nmov.b64 db, {%42, %43};\n"
      "wgmma.mma_async.sync.aligned.m64n80k16.f32.bf16.bf16 {"
      "%0, %1, %2, %3, %4, %5, %6, %7, %8, %9, %10, %11, %12, %13, %14, %15, "
      "%16, %17, %18, %19, %20, %21, %22, %23, %24, %25, %26, %27, %28, %29, %30, %31, "
      "%32, %33, %34, %35, %36, %37, %38, %39"
      "}, da, db, p, 1, 1, 0, 1;\n}\n"
      : "+f"(d[0]), "+f"(d[1]), "+f"(d[2]), "+f"(d[3]), "+f"(d[4]), "+f"(d[5]), "+f"(d[6]), "+f"(d[7]),
        "+f"(d[8]), "+f"(d[9]), "+f"(d[10]), "+f"(d[11]), "+f"(d[12]), "+f"(d[13]), "+f"(d[14]), "+f"(d[15]),
        "+f"(d[16]), "+f"(d[17]), "+f"(d[18]), "+f"(d[19]), "+f"(d[20]), "+f"(d[21]), "+f"(d[22]), "+f"(d[23]),
        "+f"(d[24]), "+f"(d[25]), "+f"(d[26]), "+f"(d[27]), "+f"(d[28]), "+f"(d[29]), "+f"(d[30]), "+f"(d[31]),
        "+f"(d[32]), "+f"(d[33]), "+f"(d[34]), "+f"(d[35]), "+f"(d[36]), "+f"(d[37]), "+f"(d[38]), "+f"(d[39])
      : "r"(da), "n"(HA), "r"(db), "n"(HB), "r"(sc));
  }
};
template <> struct WgSST<192> {
  template <uint32_t HA, uint32_t HB>
  static __device__ __forceinline__ void mma(float* d, uint32_t da, uint32_t db, int sc) {
    asm volatile("{\n.reg .pred p;\n.reg .b64 da, db;\nsetp.ne.b32 p, %100, 0;\n"
      "mov.b64 da, {%96, %97};\nmov.b64 db, {%98, %99};\n"
      "wgmma.mma_async.sync.aligned.m64n192k16.f32.bf16.bf16 {"
      "%0, %1, %2, %3, %4, %5, %6, %7, %8, %9, %10, %11, %12, %13, %14, %15, "
      "%16, %17, %18, %19, %20, %21, %22, %23, %24, %25, %26, %27, %28, %29, %30, %31, "
      "%32, %33, %34, %35, %36, %37, %38, %39, %40, %41, %42, %43, %44, %45, %46, %47, "
      "%48, %49, %50, %51, %52, %53, %54, %55, %56, %57, %58, %59, %60, %61, %62, %63, "
      "%64, %65, %66, %67, %68, %69, %70, %71, %72, %73, %74, %75, %76, %77, %78, %79, "
      "%80, %81, %82, %83, %84, %85, %86, %87, %88, %89, %90, %91, %92, %93, %94, %95"
      "}, da, db, p, 1, 1, 0, 1;\n}\n"
      : "+f"(d[0]), "+f"(d[1]), "+f"(d[2]), "+f"(d[3]), "+f"(d[4]), "+f"(d[5]), "+f"(d[6]), "+f"(d[7]),
        "+f"(d[8]), "+f"(d[9]), "+f"(d[10]), "+f"(d[11]), "+f"(d[12]), "+f"(d[13]), "+f"(d[14]), "+f"(d[15]),
        "+f"(d[16]), "+f"(d[17]), "+f"(d[18]), "+f"(d[19]), "+f"(d[20]), "+f"(d[21]), "+f"(d[22]), "+f"(d[23]),
        "+f"(d[24]), "+f"(d[25]), "+f"(d[26]), "+f"(d[27]), "+f"(d[28]), "+f"(d[29]), "+f"(d[30]), "+f"(d[31]),
        "+f"(d[32]), "+f"(d[33]), "+f"(d[34]), "+f"(d[35]), "+f"(d[36]), "+f"(d[37]), "+f"(d[38]), "+f"(d[39]),
        "+f"(d[40]), "+f"(d[41]), "+f"(d[42]), "+f"(d[43]), "+f"(d[44]), "+f"(d[45]), "+f"(d[46]), "+f"(d[47]),
        "+f"(d[48]), "+f"(d[49]), "+f"(d[50]), "+f"(d[51]), "+f"(d[52]), "+f"(d[53]), "+f"(d[54]), "+f"(d[55]),
        "+f"(d[56]), "+f"(d[57]), "+f"(d[58]), "+f"(d[59]), "+f"(d[60]), "+f"(d[61]), "+f"(d[62]), "+f"(d[63]),
        "+f"(d[64]), "+f"(d[65]), "+f"(d[66]), "+f"(d[67]), "+f"(d[68]), "+f"(d[69]), "+f"(d[70]), "+f"(d[71]),
        "+f"(d[72]), "+f"(d[73]), "+f"(d[74]), "+f"(d[75]), "+f"(d[76]), "+f"(d[77]), "+f"(d[78]), "+f"(d[79]),
        "+f"(d[80]), "+f"(d[81]), "+f"(d[82]), "+f"(d[83]), "+f"(d[84]), "+f"(d[85]), "+f"(d[86]), "+f"(d[87]),
        "+f"(d[88]), "+f"(d[89]), "+f"(d[90]), "+f"(d[91]), "+f"(d[92]), "+f"(d[93]), "+f"(d[94]), "+f"(d[95])
      : "r"(da), "n"(HA), "r"(db), "n"(HB), "r"(sc));
  }
};

struct FftConst {
  uint32_t f[2][4], fi[4][4];
  float ta[4], tb[4];
};
__device__ __forceinline__ void cis(int m, float scale, float& c, float& s) {
  const float a = (float)m * (-6.283185307179586f * scale);
  c = __cosf(a);
  s = __sinf(a);
}
__device__ __forceinline__ void fft_tables(uint32_t (&v)[12], int tw) {
  const int row = tw >> 2, ch = tw & 3;
#pragma unroll
  for (int i = 0; i < 4; i++) {
    float c[2], s[2], x[2];
#pragma unroll
    for (int e = 0; e < 2; e++) {
      cis((((32 * (8 * ch + 2 * i + e) + 15) * (4 * row - 63) + 2048) & 4095) - 2048, 1.f / 4096, c[e], s[e]);
      float gc, gs;
      cis((((row & 15) * (8 * (ch & 1) + 2 * i + e) + 8) & 15) - 8, 1.f / 16, gc, gs);
      x[e] = (row >> 4) == (ch >> 1) ? gc : (ch >> 1) ? gs : -gs;
    }
    v[i] = pack2(c[0] * 0.125f, c[1] * 0.125f);
    v[4 + i] = pack2(s[0] * 0.125f, s[1] * 0.125f);
    v[8 + i] = pack2(x[0], x[1]);
  }
#pragma unroll
  for (int i = 0; i < 12; i++) asm volatile("" : "+r"(v[i]));
}
__device__ __forceinline__ void fft_tables_store(const uint32_t (&v)[12], uint32_t sb, int tw) {
  const int row = tw >> 2;
  const uint32_t x = ((tw ^ (row >> 1)) & 3) << 4, a = sb + OFF_FT + (16 * (row >> 3) + (row & 7)) * 64 + x;
  sts128(a, v[0], v[1], v[2], v[3]);
  sts128(a + 512, v[4], v[5], v[6], v[7]);
  sts128(sb + OFF_GT + row * 64 + x, v[8], v[9], v[10], v[11]);
}
__device__ __forceinline__ void fft_twiddles(float (&v)[4], int tw) {
#pragma unroll
  for (int i = 0; i < 2; i++) {
    float c, s;
    cis((2 * (2 * (tw & 3) + i) - 15) * (4 * (tw >> 2) - 63), 1.f / 4096, c, s);
    v[2 * i] = __fdividef(-s, 1.f + c);
    v[2 * i + 1] = s;
  }
  pin<4>(v);
}
__device__ __forceinline__ void fft_matrices(FftConst& k, uint32_t sb, int w, int lane) {
  const uint32_t x = (lane >> 1) & 3;
  const uint4 t0 = lds128(sb + OFF_TT + 512 * w + 16 * lane), t1 = lds128(sb + OFF_TT + 512 * w + 16 * (lane ^ 3));
  k.ta[0] = __uint_as_float(t0.x); k.tb[0] = __uint_as_float(t0.y); k.ta[1] = __uint_as_float(t0.z); k.tb[1] = __uint_as_float(t0.w);
  k.ta[3] = __uint_as_float(t1.x); k.tb[3] = __uint_as_float(t1.y); k.ta[2] = __uint_as_float(t1.z); k.tb[2] = __uint_as_float(t1.w);
#pragma unroll
  for (int i = 0; i < 2; i++) {
    ldsm4(k.f[i], sb + OFF_FT + (16 * w + (lane & 15)) * 64 + (((2 * i + (lane >> 4)) ^ x) << 4));
    ldsm4t(k.fi[i], sb + OFF_FT + (32 * i + lane) * 64 + ((w ^ x) << 4));
#pragma unroll
    for (int j = 0; j < 4; j++) {
      k.fi[2 + i][j] = (j & 1) ? k.fi[i][j - 1] ^ 0x80008000u : k.fi[i][j + 1];
      asm volatile("" : "+r"(k.fi[2 + i][j]));
    }
  }
}
__device__ __forceinline__ void rot(bool inv, float& x, float& y, float a, float b) {
  x = fmaf(inv ? -a : a, y, x);
  y = fmaf(inv ? -b : b, x, y);
  x = fmaf(inv ? -a : a, y, x);
}
__device__ __forceinline__ void twiddle_fwd(uint32_t (&a)[4][4], float* d, const FftConst& k) {
#pragma unroll
  for (int q = 0; q < 4; q++)
#pragma unroll
    for (int j = 0; j < 2; j++) {
      float* x = d + 8 * q + 4 * j;
      rot(j, x[0], x[2], k.ta[2 * j], k.tb[2 * j]);
      rot(j, x[1], x[3], k.ta[2 * j + 1], k.tb[2 * j + 1]);
      a[q & 2][2 * j + (q & 1)] = pack2(x[0], x[1]);
      a[(q & 2) + 1][2 * j + (q & 1)] = pack2(x[2], x[3]);
    }
}
__device__ __forceinline__ void g_step(float* d, const uint32_t (&a)[4][4], uint32_t dre, uint32_t dim) {
  WgRS<32>::set<HI_SW64>(d, a[0], dre);
  WgRS<32>::set<HI_SW64>(d + 16, a[2], dre);
  WgRS<32>::mma<HI_SW64>(d, a[1], dim);
  WgRS<32>::mma<HI_SW64>(d + 16, a[3], dim);
  wg_commit();
}

__device__ __forceinline__ void conv_channel(const FftConst& k, uint32_t sb, int c, int wg, int w, int lane) {
  const uint32_t cb = sb + off_ch(c), bars = sb + OFF_BAR;
  const uint32_t du = desc_lo(cb, 1024), dg = desc_lo(sb + OFF_GT, 16), dz = desc_lo(cb + U_BYTES, 16);
  float U[32], H[32];
  uint32_t a[4][4], e[4][4];
  const float dv = __uint_as_float(lds32(sb + OFF_D + 4 * c));
  wg_fence();
  WgRS<64>::set<HI_SW32>(H, k.f[0], du + 256);
  WgRS<64>::mma<HI_SW32>(H, k.f[1], du + 256 + 32);
  wg_commit();
  wg_wait<0>();
  pin<32>(H);
  twiddle_fwd(a, H, k);
  if (ATT_GATE && H_EARLY) mbar_wait(bars + 8 * B_ATTN, 0);
  mbar_wait(bars + 8 * (B_U + (c < 3 ? c : 3)), 0);
  TSM(w == 0 && c < 3, 7 + wg);
  wg_fence();
  WgRS<64>::set<HI_SW32>(U, k.f[0], du);
  WgRS<64>::mma<HI_SW32>(U, k.f[1], du + 32);
  wg_commit();
  g_step(H, a, dg, dg + 64);
  wg_wait<1>();
  pin<32>(U);
  twiddle_fwd(e, U, k);
  wg_fence();
  g_step(U, e, dg, dg + 64);
  wg_wait<0>();
  pin<32>(U);
  pin<32>(H);
#pragma unroll
  for (int j = 0; j < 2; j++) {
    float pr[4][2], pi[4][2];
#pragma unroll
    for (int x = 0; x < 2; x++) {
      H[4 * j + x] += dv;
#pragma unroll
      for (int m = 0; m < 4; m++) {
#pragma unroll
        for (int q = 0; q <= m; q++) {
          const int ih = 16 * (q >> 1) + 2 * (q & 1) + 4 * j + x, iu = 16 * ((m - q) >> 1) + 2 * ((m - q) & 1) + 4 * j + x;
          pr[m][x] = q ? fmaf(H[ih], U[iu], pr[m][x]) : H[ih] * U[iu];
          pi[m][x] = q ? fmaf(H[ih], U[iu + 8], pi[m][x]) : H[ih] * U[iu + 8];
          pr[m][x] = fmaf(-H[ih + 8], U[iu + 8], pr[m][x]);
          pi[m][x] = fmaf(H[ih + 8], U[iu], pi[m][x]);
        }
      }
    }
#pragma unroll
    for (int m = 0; m < 4; m++) {
      a[m & 2][2 * j + (m & 1)] = pack2(pr[m][0], pr[m][1]);
      a[(m & 2) + 1][2 * j + (m & 1)] = pack2(pi[m][0], pi[m][1]);
    }
  }
  wg_fence();
  g_step(U, a, dg + 64, dg);
  const uint32_t za = cb + U_BYTES + (8 * w + (lane & 7)) * 128 + (((lane >> 3) ^ (lane & 7)) << 4);
  const uint32_t ya = cb + (lane >> 4) * 1024 + (8 * w + (lane & 7)) * 32 + ((((lane >> 3) ^ (lane >> 2)) & 1) << 4);
  wg_sync(1 + wg);
  wg_wait<0>();
  pin<32>(U);
  TSIF(w == 0, 80 + c);
#pragma unroll
  for (int p = 0; p < 2; p++) {
#pragma unroll
    for (int i = 0; i < 4; i++) {
      const int j = i & 1;
      float* x = U + 16 * p + 4 * j + (i & 2);
      rot(!j, x[8], x[0], k.ta[2 * j], k.tb[2 * j]);
      rot(!j, x[9], x[1], k.ta[2 * j + 1], k.tb[2 * j + 1]);
      e[p][i] = pack2(x[8], x[9]);
      e[2 + p][i] = pack2(x[0], x[1]);
    }
    stsm4(za ^ (64 * p), e[p]);
    stsm4((za ^ (64 * p)) + 4096, e[2 + p]);
  }
  fence_async_smem();
  wg_sync(1 + wg);
  wg_fence();
  WgRS<64>::set<HI_SW128>(H, k.fi[0], dz);
#pragma unroll
  for (int ks = 1; ks < 4; ks++) WgRS<64>::mma<HI_SW128>(H, k.fi[ks], dz + 128 * ks);
  wg_commit();
  wg_wait<0>();
  pin<32>(H);
  TSIF(w == 0, 88 + c);
#pragma unroll
  for (int j = 0; j < 8; j++)
    a[j >> 2][j & 3] = j < 2 ? pack2(H[4 * j], H[4 * j + 1]) : pack2(H[4 * j] + H[4 * j - 6], H[4 * j + 1] + H[4 * j - 5]);
  stsm4(ya, a[0]);
  stsm4(ya + 2048, a[1]);
  fence_async_smem();
  __syncwarp();
}

__device__ __forceinline__ void prep_slab(uint4* res, const uint2* sw, uint32_t sb, int slab, int w, int lane) {
  const int t = lane & 3, tp = (lane & 7) >> 1, pos = 8 * tp + 2 * (((lane >> 3) + tp) & 3) + (lane & 1);
  const uint32_t base = sb + OFF_KVS + slab * KVS_BYTES + pos * 128;
  uint32_t kk[2][4][4], vv[2][4];
  mbar_wait(sb + OFF_BAR + 8 * (B_KV + slab), 0);
#pragma unroll
  for (int h = 0; h < 2; h++) {
#pragma unroll
    for (int j = 0; j < 4; j++) {
      const uint32_t a = base + 128 * j;
      ldsm4t(kk[h][j], a + (((w + 4 * h) ^ ((a >> 7) & 7)) << 4));
    }
    const uint32_t a = base + KVS_V;
    ldsm4t(vv[h], a + (((w + 4 * h) ^ ((a >> 7) & 7)) << 4));
  }
#pragma unroll
  for (int h = 0; h < 2; h++) {
    uint32_t (&k)[4][4] = kk[h];
    uint32_t (&v)[4] = vv[h];
    const uint32_t w0 = __byte_perm(sw[h].x, 0, 0x1010), w1 = __byte_perm(sw[h].x, 0, 0x3232);
    const uint32_t w2 = __byte_perm(sw[h].y, 0, 0x1010), w3 = __byte_perm(sw[h].y, 0, 0x3232);
#pragma unroll
    for (int m = 0; m < 4; m++)
      v[m] = bmul(badd(badd(badd(bmul(k[0][m], w3), bmul(k[1][m], w2)), bmul(k[2][m], w1)), bmul(k[3][m], w0)), v[m]);
    uint32_t a[4];
#pragma unroll
    for (int m = 0; m < 4; m++) a[m] = (t & 1) ? v[(m + 3) & 3] : v[m];
    res[h] = (t & 2) ? make_uint4(a[2], a[3], a[0], a[1]) : make_uint4(a[0], a[1], a[2], a[3]);
  }
}

__device__ __forceinline__ void gate_rows(const Params& p, const uint2 (&gw)[5], int row, int lane) {
  uint2 x[4][5];
#pragma unroll
  for (int i = 0; i < 4; i++)
#pragma unroll
    for (int j = 0; j < 5; j++) x[i][j] = ldg64(reinterpret_cast<const uint2*>(p.q) + (row + i) * (DIM / 4) + lane + 32 * j);
  float s[4];
#pragma unroll
  for (int i = 0; i < 4; i++) {
    s[i] = 0.f;
#pragma unroll
    for (int j = 0; j < 5; j++) {
      const uint32_t m0 = bmul(x[i][j].x, gw[j].x), m1 = bmul(x[i][j].y, gw[j].y);
      s[i] += (bf_lo(m0) + bf_hi(m0)) + (bf_lo(m1) + bf_hi(m1));
    }
  }
  const bool h = lane & 16, q = lane & 8;
  const float a = (h ? s[2] : s[0]) + __shfl_xor_sync(0xffffffffu, h ? s[0] : s[2], 16);
  const float c = (h ? s[3] : s[1]) + __shfl_xor_sync(0xffffffffu, h ? s[1] : s[3], 16);
  float z = (q ? c : a) + __shfl_xor_sync(0xffffffffu, q ? a : c, 8);
#pragma unroll
  for (int o = 4; o > 0; o >>= 1) z += __shfl_xor_sync(0xffffffffu, z, o);
  z = bf_lo(pack2(z, 0.f));
  if ((lane & 7) == 0) g_gate[row + (lane >> 3)] = bf_lo(pack2(__fdividef(1.f, 1.f + __expf(-z)), 0.f));
}

__device__ __forceinline__ void helper_cta(const Params& p, uint32_t sb, int hb, int tid) {
  const int lane = tid & 31;
  if (tid < 256) {
    constexpr uint32_t PITCH = 1312;
    const uint32_t bar = sb + OFF_BAR;
    if (tid == 0) {
      mbar_init(bar, 1);
      mbar_init(bar + 8, 1);
      fence_async_smem();
      mbar_expect_tx(bar, 80 * 1280);
      mbar_expect_tx(bar + 8, 80 * 1280);
    }
    asm volatile("bar.sync 1, 256;" ::: "memory");
    if (tid < 160) bulk_load(sb + tid * PITCH, p.wo + (160 * hb + tid) * DIM, 1280, bar + (tid < 80 ? 0 : 8));
#pragma unroll 1
    for (int kb = 0; kb < 2; kb++) {
      mbar_wait(bar + 8 * kb, 0);
#pragma unroll 5
      for (int i = tid; i < 6400; i += 256) {
        const int hg = i / 800, c = i - 800 * hg, n = c / 160, row = (c - 160 * n) >> 1;
        g_WO[(hg * 8 + 2 * hb + kb) * 800 + c] = lds128(sb + (80 * kb + row) * PITCH + 160 * hg + 32 * n + 16 * ((c ^ (row >> 2)) & 1));
      }
    }
    asm volatile("bar.sync 1, 256;" ::: "memory");
    if (tid < 32) flag_signal(g_cnt + C_W, 8, lane);
  } else {
    uint2 gw[5];
#pragma unroll
    for (int j = 0; j < 5; j++) gw[j] = ldg64(reinterpret_cast<const uint2*>(p.gate_w) + lane + 32 * j);
#pragma unroll 1
    for (int i = 0; i < 16; i++) gate_rows(p, gw, 512 * hb + 32 * i + 4 * ((tid >> 5) - 8), lane);
    asm volatile("bar.sync 2, 256;" ::: "memory");
    if (tid < 288) flag_signal(g_cnt + C_G, 8, lane);
  }
}

__device__ __forceinline__ uint32_t bmax(uint32_t a, uint32_t b) {
  uint32_t d;
  asm("max.bf16x2 %0, %1, %2;" : "=r"(d) : "r"(a), "r"(b));
  return d;
}
__device__ __forceinline__ void softmax_two(const float (&l)[2][2], uint32_t& p0, uint32_t& p1) {
  constexpr float kScale = 0.22360679774997896f, kLog2e = 1.4426950408889634f;
  const uint32_t r0 = pack2(l[0][0], l[1][0]), r1 = pack2(l[0][1], l[1][1]);
  const uint32_t x0 = pack2(bf_lo(r0) * kScale, bf_hi(r0) * kScale), x1 = pack2(bf_lo(r1) * kScale, bf_hi(r1) * kScale);
  uint32_t m = bmax(x0, x1);
  m = bmax(m, __shfl_xor_sync(0xffffffffu, m, 1));
  m = bmax(m, __shfl_xor_sync(0xffffffffu, m, 2));
  const float m0 = bf_lo(m) * kLog2e, m1 = bf_hi(m) * kLog2e;
  p0 = pack2(ex2(bf_lo(x0) * kLog2e - m0), ex2(bf_lo(x1) * kLog2e - m0));
  p1 = pack2(ex2(bf_hi(x0) * kLog2e - m1), ex2(bf_hi(x1) * kLog2e - m1));
}

__device__ __forceinline__ void halo_read(uint32_t (&kpv)[10], uint32_t (&vpv)[10], uint32_t (&tg)[7], const uint4* hp) {
#pragma unroll
  for (int j = 0; j < 7; j++) {
    uint32_t x0, x1, x2;
    asm volatile("ld.relaxed.gpu.global.v4.u32 {%0, %1, %2, %3}, [%4];"
                 : "=r"(x0), "=r"(x1), "=r"(x2), "=r"(tg[j]) : "l"(hp + 32 * j) : "memory");
    if (j < 4) kpv[3 * j] = x0; else vpv[3 * j - 10] = x0;
    if (j < 3) kpv[3 * j + 1] = x1; else vpv[3 * j - 9] = x1;
    if (j < 3) kpv[3 * j + 2] = x2; else if (j < 6) vpv[3 * j - 8] = x2;
  }
}

template <int ROT>
__device__ __forceinline__ void pack_qkv(const float* acc, uint32_t (&qlo)[10], uint32_t (&qhi)[10], uint32_t (&klo)[10],
                                         uint32_t (&khi)[10], uint32_t (&vlo)[10], uint32_t (&vhi)[10]) {
#pragma unroll
  for (int j = 0; j < 10; j++) {
    const int x = (j + ROT) % 10, tq = x < 8 ? x : 16 + x, tk = x < 8 ? 8 + x : 18 + x, tv = x < 8 ? 16 + x : 20 + x;
    khi[j] = pack2(acc[4 * tk + 2], acc[4 * tk + 3]);
    vhi[j] = movm(pack2(acc[4 * tv + 2], acc[4 * tv + 3]));
    qlo[j] = pack2(acc[4 * tq], acc[4 * tq + 1]);
    qhi[j] = pack2(acc[4 * tq + 2], acc[4 * tq + 3]);
    klo[j] = pack2(acc[4 * tk], acc[4 * tk + 1]);
    vlo[j] = pack2(acc[4 * tv], acc[4 * tv + 1]);
    asm volatile("" : "+r"(khi[j]), "+r"(qlo[j]), "+r"(qhi[j]), "+r"(klo[j]), "+r"(vlo[j]));
  }
}

template <int ROT> __device__ __forceinline__ void halo_send(const float* acc, uint4* ho, uint32_t tag) {
#pragma unroll
  for (int j = 0; j < 7; j++) {
    uint32_t x[3];
#pragma unroll
    for (int e = 0; e < 3; e++) {
      const int i = 3 * j + e, y = (i % 10 + ROT) % 10, tk = y < 8 ? 8 + y : 18 + y, tv = y < 8 ? 16 + y : 20 + y;
      x[e] = i < 10 ? pack2(acc[4 * tk + 2], acc[4 * tk + 3]) : i < 20 ? movm(pack2(acc[4 * tv + 2], acc[4 * tv + 3])) : 0u;
    }
    asm volatile("st.relaxed.gpu.global.v4.u32 [%0], {%1, %2, %3, %4};" ::"l"(ho + 32 * j), "r"(x[0]), "r"(x[1]), "r"(x[2]), "r"(tag) : "memory");
  }
}

__device__ __forceinline__ void attention(float* acc, uint32_t sb, int b, int par, int w, int lane, uint32_t tag) {
  const int g = lane >> 2, t = lane & 3;
  uint32_t klo[10], khi[10], vlo[10], vhi[10], qlo[10], qhi[10], kpv[10], vpv[10];
  if (HALO_FIRST && w == 3 && b < NCTA - 8) {
    uint4* ho = g_halo + (b * 2 + par) * 224 + lane;
    if (tail_first(b & 7)) halo_send<8>(acc, ho, tag);
    else halo_send<0>(acc, ho, tag);
    TSIF(par == 0, 76);
    pin<120>(acc);
  }
  if (tail_first(b & 7)) pack_qkv<8>(acc, qlo, qhi, klo, khi, vlo, vhi);
  else pack_qkv<0>(acc, qlo, qhi, klo, khi, vlo, vhi);
  const uint32_t xa = sb + OFF_KVX + (par * 3) * 2560 + lane * 16;
  if (w < 3) {
    sts128(xa + w * 2560, khi[0], khi[1], khi[2], khi[3]);
    sts128(xa + w * 2560 + 512, khi[4], khi[5], khi[6], khi[7]);
    sts128(xa + w * 2560 + 1024, khi[8], khi[9], vhi[0], vhi[1]);
    sts128(xa + w * 2560 + 1536, vhi[2], vhi[3], vhi[4], vhi[5]);
    sts128(xa + w * 2560 + 2048, vhi[6], vhi[7], vhi[8], vhi[9]);
  } else if (!HALO_FIRST && b < NCTA - 8) {
    uint4* ho = g_halo + (b * 2 + par) * 224 + lane;
#pragma unroll
    for (int j = 0; j < 7; j++) {
      const uint32_t x0 = j < 4 ? khi[3 * j] : vhi[3 * j - 10], x1 = j < 3 ? khi[3 * j + 1] : vhi[3 * j - 9];
      const uint32_t x2 = j < 3 ? khi[3 * j + 2] : j < 6 ? vhi[3 * j - 8] : 0u;
      asm volatile("st.relaxed.gpu.global.v4.u32 [%0], {%1, %2, %3, %4};" ::"l"(ho + 32 * j), "r"(x0), "r"(x1), "r"(x2), "r"(tag) : "memory");
    }
  }
  TSIF(par == 0 && w == 1, 64);
  TSIF(par == 0 && w == 3 && !HALO_FIRST, 76);
#pragma unroll
  for (int j = 0; j < 10; j++) vlo[j] = movm(vlo[j]);
  const bool far0 = 2 * t > g, far1 = 2 * t + 1 > g;
  const uint32_t mfar = (far0 ? 0x0000FFFFu : 0u) | (far1 ? 0xFFFF0000u : 0u);
  float slo[4][2], shi[4][2], lg[2][2];
  uint32_t phi[4], plo[4], qml[4], qmh[4];
#pragma unroll
  for (int h = 0; h < 4; h++) {
    const int f = h == 0 ? 0 : h == 1 ? 3 : h == 2 ? 5 : 8, hf = h < 2 ? 2 : 7;
    const bool mine = (h & 1) ? t >= 2 : t < 2;
    qml[h] = mine ? qlo[hf] : 0u;
    qmh[h] = mine ? qhi[hf] : 0u;
    float a[4] = {0.f, 0.f, 0.f, 0.f}, c[4] = {0.f, 0.f, 0.f, 0.f};
    mma16816(a, qlo[f], qhi[f], qlo[f + 1], qhi[f + 1], klo[f], klo[f + 1]);
    mma16816(c, qlo[f], qhi[f], qlo[f + 1], qhi[f + 1], khi[f], khi[f + 1]);
    mma1688(a, qml[h], qmh[h], klo[hf]);
    mma1688(c, qml[h], qmh[h], khi[hf]);
    slo[h][0] = a[0];
    slo[h][1] = a[1];
    shi[h][0] = lg[h & 1][0] = far0 ? a[2] : c[2];
    shi[h][1] = lg[h & 1][1] = far1 ? a[3] : c[3];
    if (!ATT_MERGE && (h & 1)) softmax_two(lg, phi[h - 1], phi[h]);
  }
  TSIF(par == 0 && w == 1, 65);
  wg_sync(1 + par);
  TSIF(par == 0 && w == 1, 66);
  const bool nohist = (w == 0) && (b < 8);
  const uint4* hp = g_halo + ((b - 8) * 2 + par) * 224 + lane;
  uint32_t tg[7];
  if (w > 0) {
    const uint4 v0 = lds128(xa + (w - 1) * 2560), v1 = lds128(xa + (w - 1) * 2560 + 512), v2 = lds128(xa + (w - 1) * 2560 + 1024);
    const uint4 v3 = lds128(xa + (w - 1) * 2560 + 1536), v4 = lds128(xa + (w - 1) * 2560 + 2048);
    kpv[0] = v0.x; kpv[1] = v0.y; kpv[2] = v0.z; kpv[3] = v0.w; kpv[4] = v1.x; kpv[5] = v1.y; kpv[6] = v1.z; kpv[7] = v1.w;
    kpv[8] = v2.x; kpv[9] = v2.y; vpv[0] = v2.z; vpv[1] = v2.w; vpv[2] = v3.x; vpv[3] = v3.y; vpv[4] = v3.z; vpv[5] = v3.w;
    vpv[6] = v4.x; vpv[7] = v4.y; vpv[8] = v4.z; vpv[9] = v4.w;
  } else if (nohist) {
#pragma unroll
    for (int j = 0; j < 10; j++) kpv[j] = vpv[j] = 0u;
  } else {
    TSIF(par == 0, 77);
    halo_read(kpv, vpv, tg, hp);
  }
  if (w == 0 && !nohist) {
    int spins = 0;
    while (true) {
      bool ok = true;
#pragma unroll
      for (int j = 0; j < 7; j++) ok = ok && tg[j] == tag;
      if (__all_sync(0xffffffffu, ok) || ++spins > SPIN_LIMIT) break;
      halo_read(kpv, vpv, tg, hp);
    }
    TSIF(par == 0, 79);
  }
#pragma unroll
  for (int h = 0; h < 4; h++) {
    const int f = h == 0 ? 0 : h == 1 ? 3 : h == 2 ? 5 : 8, hf = h < 2 ? 2 : 7;
    float a[4] = {0.f, 0.f, 0.f, 0.f};
    mma16816(a, qlo[f], qhi[f], qlo[f + 1], qhi[f + 1], kpv[f], kpv[f + 1]);
    mma1688(a, qml[h], qmh[h], kpv[hf]);
    const float ninf = __int_as_float(0xff800000);
    lg[h & 1][0] = far0 ? (nohist ? ninf : a[0]) : slo[h][0];
    lg[h & 1][1] = far1 ? (nohist ? ninf : a[1]) : slo[h][1];
    if (h & 1) {
      softmax_two(lg, plo[h - 1], plo[h]);
      if (ATT_MERGE) {
        const float lh[2][2] = {{shi[h - 1][0], shi[h - 1][1]}, {shi[h][0], shi[h][1]}};
        softmax_two(lh, phi[h - 1], phi[h]);
      }
    }
  }
  TSIF(par == 0 && w <= 1, 67 + w);
  uint32_t ov[20];
#pragma unroll
  for (int hp = 0; hp < 2; hp++) {
    const int hf = hp ? 7 : 2;
    float sh[4] = {0.f, 0.f, 0.f, 0.f}, i0 = 0.f, i1 = 0.f;
#pragma unroll
    for (int e = 0; e < 2; e++) {
      const int h = 2 * hp + e, f = h == 0 ? 0 : h == 1 ? 3 : h == 2 ? 5 : 8;
      const uint32_t a0 = plo[h] & mfar, a2 = plo[h] & ~mfar, a3 = phi[h] & mfar, c1 = phi[h] & ~mfar;
      float sum[4] = {0.f, 0.f, 0.f, 0.f};
      mma1688(sum, plo[h], phi[h], 0x3F803F80u);
      const float r0 = rcp(sum[0]), r1 = rcp(sum[2]);
#pragma unroll
      for (int j = f; j < f + 2; j++) {
        float o[4] = {0.f, 0.f, 0.f, 0.f};
        mma16816(o, a0, 0u, a2, a3, vpv[j], vlo[j]);
        mma1688(o, 0u, c1, vhi[j]);
        ov[2 * j] = pack2(o[0] * r0, o[1] * r0);
        ov[2 * j + 1] = pack2(o[2] * r1, o[3] * r1);
      }
      const bool mine = e ? g >= 4 : g < 4;
      mma16816(sh, a0, 0u, a2, a3, mine ? vpv[hf] : 0u, mine ? vlo[hf] : 0u);
      mma1688(sh, 0u, c1, mine ? vhi[hf] : 0u);
      if (e == 0 || t >= 2) {
        i0 = r0;
        i1 = r1;
      }
    }
    ov[2 * hf] = pack2(sh[0] * i0, sh[1] * i0);
    ov[2 * hf + 1] = pack2(sh[2] * i1, sh[3] * i1);
  }
  TS(32 + 4 * par + w);
  mbar_wait(sb + OFF_BAR + 8 * B_P1, 0);
  const uint32_t oa = sb + OFF_OA + (lane >> 4) * 2048 + (32 * w + 2 * (lane & 15) + par) * 16;
#pragma unroll
  for (int j = 0; j < 5; j++) stsm4(oa + 4096 * j, ov + 4 * j);
  TSIF(par == 0 && w == 0, 120);
  fence_async_smem();
  TSIF(par == 0 && w == 0, 121);
  __syncwarp();
  if (lane == 0) mbar_arrive(sb + OFF_BAR + 8 * B_ATTN);
  TSM(w == 0 || w == 2, 122 + par + (w == 2 ? 3 : 0));
}

struct Maps {
  CUtensorMap x, wm, wt, k, v, y, qm, qt, om, ot, u;
};

__device__ __forceinline__ void load_stage(uint32_t sb, int kb, int b, const Maps& m) {
  const uint32_t st = sb + (kb & 3) * STAGE_BYTES, bar = sb + OFF_BAR + 8 * (B_FULL1 + (kb & 3));
  const int r = b >> 3, hg = b & 7, slab = kb - KV_KB;
  const bool kv = slab >= 0 && slab < 5;
  const uint32_t kbar = sb + OFF_BAR + 8 * (B_KV + slab), dst = sb + OFF_KVS + slab * KVS_BYTES;
  mbar_expect_tx(bar, STAGE_BYTES);
  if (kv) mbar_expect_tx(kbar, KVS_BYTES);
  tma_3d(st, &m.x, 64 * kb, 64 * r, 0, bar);
  if (kv && KV_MIX) tma_3d(dst, &m.k, 0, 32 * (b >> 1) - 3, 2 * slab + (b & 1), kbar);
  tma_3d(st + ST_W, &m.wm, 80 * hg + (tail_first(hg) ? 16 : 0), 64 * kb, 0, bar);
  if (kv && KV_MIX) tma_3d(dst + KVS_V, &m.v, 0, 32 * (b >> 1), 2 * slab + (b & 1), kbar);
  tma_3d(st + ST_WT, &m.wt, 80 * hg + (tail_first(hg) ? 0 : 64), 64 * kb, 0, bar);
  if (kv && !KV_MIX) tma_3d(dst, &m.k, 0, 32 * (b >> 1) - 3, 2 * slab + (b & 1), kbar);
  if (kv && !KV_MIX) tma_3d(dst + KVS_V, &m.v, 0, 32 * (b >> 1), 2 * slab + (b & 1), kbar);
}

__global__ void __launch_bounds__(NTHR, 1) fused_kernel(const __grid_constant__ Maps m, const Params p) {
  extern __shared__ __align__(1024) uint8_t smem[];
  const uint32_t sb = (uint32_t)__cvta_generic_to_shared(smem);
  const uint32_t bars = sb + OFF_BAR;
  const int tid = threadIdx.x, lane = tid & 31;
  int b = blockIdx.x;
  if (b >= NCTA) {
    helper_cta(p, sb, b - NCTA, tid);
    return;
  }
  if (BMAP == 1) b = (((b & 63) >> 3) * 2 + (b & 1)) * 8 + (((b < 64 ? 0x6521 : 0x7430) >> (4 * ((b >> 1) & 3))) & 7);
  if (BMAP == 2) b = ((b & 63) >> 2) * 8 + (((b < 64 ? 0x6521 : 0x7430) >> (4 * (b & 3))) & 7);
  if (BMAP == 3) b = (((b & 63) >> 3) * 2 + (b & 1)) * 8 + (((b < 64 ? 0x7430 : 0x6521) >> (4 * ((b >> 1) & 3))) & 7);
  if (BMAP == 4) b = (((b >> 4) * 2 + (b & 1)) * 8) + ((b >> 1) & 7);
  if (BMAP == 5) b = 127 - b;
  const int r = b >> 3, hg = b & 7;

  if (tid == T_ISSUE) {
    TSM(true, 0);
#pragma unroll
    for (int i = 0; i < 4; i++) mbar_init(bars + 8 * (B_FULL1 + i), 1);
#pragma unroll
    for (int i = 0; i < 3; i++) mbar_init(bars + 8 * (B_KV + i), 1);
    fence_async_smem();
#pragma unroll 1
    for (int kb = 0; kb <= PRE2; kb++) load_stage(sb, kb, b, m);
  } else if (tid >= T_PF && tid < T_PF + 11) {
    tm_prefetch(&m.x + (tid - T_PF));
  } else if (tid == T_INIT) {
#pragma unroll
    for (int i = 0; i < 4; i++) mbar_init(bars + 8 * (B_EMPTY1 + i), 8);
#pragma unroll
    for (int i = 0; i < 8; i++) mbar_init(bars + 8 * (B_FULL2 + i), 1);
#pragma unroll
    for (int i = 0; i < 4; i++) mbar_init(bars + 8 * (B_EMPTY2 + i), 8);
#pragma unroll
    for (int i = 0; i < 4; i++) mbar_init(bars + 8 * (B_U + i), 1);
    mbar_init(bars + 8 * B_HA, 4);
    mbar_init(bars + 8 * B_HB, 1);
    mbar_init(bars + 8 * B_KVD, 4);
    mbar_init(bars + 8 * B_QF, 1);
    mbar_init(bars + 8 * B_ATTN, 8);
    mbar_init(bars + 8 * B_P1, 8);
    mbar_init(bars + 8 * B_C34, 1);
#pragma unroll
    for (int i = 0; i < 5; i++) mbar_init(bars + 8 * (B_YST + i), 4);
#pragma unroll
    for (int i = 0; i < 5; i++) mbar_init(bars + 8 * (B_US + i), 4);
    mbar_init(bars + 8 * B_YSIG, 1);
    mbar_init(bars + 8 * B_YFULL, 1);
    mbar_init(bars + 8 * B_EPOCH, 1);
    mbar_init(bars + 8 * B_PREP, 4);
    mbar_init(bars + 8 * B_USIG, 1);
#pragma unroll
    for (int i = 3; i < 5; i++) mbar_init(bars + 8 * (B_KV + i), 1);
    mbar_init(bars + 8 * B_E3, 8);
    mbar_init(bars + 8 * B_LAST, 1);
    mbar_init(bars + 8 * B_OSIG, 1);
    fence_async_smem();
  }
  const int warp = __shfl_sync(0xffffffffu, tid >> 5, 0), wg = warp >> 2, w = warp & 3;
  __syncthreads();

  if (wg == 3) {
    asm volatile("setmaxnreg.dec.sync.aligned.u32 56;");
    if (w == 0) {
      if (lane == 0) {
#pragma unroll 1
        for (int kb = 1 + PRE2; kb < 10; kb++) {
          if (kb >= 4) mbar_wait(bars + 8 * (kb == 7 ? B_E3 : B_EMPTY1 + (kb & 3)), (kb >> 3) & 1);
          TSIF(kb >= 4, 44 + kb);
          load_stage(sb, kb, b, m);
          TSIF(kb == 3, 60);
          if (kb == TRIG_KB) mbar_arrive(bars + 8 * B_LAST);
        }
        mbar_wait(bars + 8 * B_P1, 0);
        mbar_wait(bars + 8 * WL_TRIG, 0);
        mbar_wait(bars + 8 * B_EPOCH, 0);
        const unsigned helped = (lds32(sb + OFF_EPOCH) + 1) * NHELP;
        flag_wait(g_cnt + C_W + 32 * hg, helped);
        TS(30);
#pragma unroll 1
        for (int j = 0; j < 8; j++) {
          if (j >= 6) mbar_wait(bars + 8 * (B_EMPTY2 + j - 6), 0);
          if (j == 4) mbar_wait(bars + 8 * B_ATTN, 0);
          TSIF(j >= 6, 100 + j);
          if (RF_GATE && j == 6) mbar_wait(bars + 8 * B_YSIG, 0);
          mbar_expect_tx(bars + 8 * (B_FULL2 + j), j == 0 ? WO_BYTES : j == 5 ? O_BYTES + WO_BYTES + 512 : O_BYTES + WO_BYTES);
          bulk_load(sb + off_w(j), g_WO + (hg * 8 + step_src(hg, j)) * 800, WO_BYTES, bars + 8 * (B_FULL2 + j));
          if (j == 5) {
            flag_wait(g_cnt + C_G + 32 * hg, helped);
            TS(72);
            bulk_load(sb + OFF_GATE, g_gate + 128 * r, 512, bars + 8 * (B_FULL2 + 5));
          }
        }
        mbar_wait(bars + 8 * (B_EMPTY2 + 3), 0);
        mbar_expect_tx(bars + 8 * B_QF, O_BYTES);
        tma_2d(sb + OFF_QS, &m.qm, 80 * hg, 128 * r, bars + 8 * B_QF);
        tma_2d(sb + OFF_QT, &m.qt, 80 * hg + 64, 128 * r, bars + 8 * B_QF);
      }
    } else if (w == 1) {
      unsigned epoch = 0;
      if (lane == 0) {
        epoch = atomicAdd(g_cnt + C_LAUNCH, 1u) / NCTA;
        asm volatile("st.shared.u32 [%0], %1;" ::"r"(sb + OFF_EPOCH), "r"(epoch) : "memory");
        mbar_arrive(bars + 8 * B_EPOCH);
        mbar_wait(bars + 8 * B_KVD, 0);
        mbar_expect_tx(bars + 8 * B_HB, 5 * 4096);
#pragma unroll 1
        for (int c = 0; c < 5; c++) {
          if (c == 3) mbar_wait(bars + 8 * B_S3, 0);
          bulk_load(sb + off_ch(c) + U_BYTES, p.ssm_k + (5 * b + c) * SEQ, 4096, bars + 8 * B_HB);
        }
#pragma unroll
        for (int c = 0; c < 4; c++) mbar_expect_tx(bars + 8 * (B_U + c), c < 3 ? U_BYTES : 2 * U_BYTES);
        const uint4* usrc = g_U + 5 * b * U_PITCH;
        mbar_wait(bars + 8 * B_USIG, 0);
        flag_wait(g_cnt + C_PREP + 32 * (b & 15), (epoch + 1) * NCTA);
        TS(23);
#pragma unroll
        for (int c = 0; c < 5; c++) {
          if (c == 3) mbar_wait(bars + 8 * (B_U + 2), 0);
          bulk_load(sb + off_ch(c), usrc + c * U_PITCH, U_BYTES, bars + 8 * (B_U + (c < 3 ? c : 3)));
          TSIF(c == 0 || c == 4, 116 + (c >> 2));
        }
      }
      epoch = __shfl_sync(0xffffffffu, epoch, 0);
      if (lane < 8) {
        const int src = (b & ~7) | step_src(hg, lane);
        mbar_wait(bars + 8 * B_OSIG, 0);
        TS(20);
        flag_wait(g_cnt + C_O + 32 * src, epoch + 1);
        if (lane >= 1 && lane < 4) bulk_load(sb + off_o(lane), g_O + src * 1280, O_BYTES, bars + 8 * (B_FULL2 + lane));
        __syncwarp(0xff);
        TS(21);
#pragma unroll 1
        for (int j = 4; j < 8; j++) {
          if (lane == j) {
            mbar_wait(bars + 8 * (j < 6 ? B_C34 : B_EMPTY2 + j - 6), 0);
            if (RF_GATE && j == 6) mbar_wait(bars + 8 * B_YSIG, 0);
            bulk_load(sb + off_o(j), g_O + src * 1280, O_BYTES, bars + 8 * (B_FULL2 + j));
          }
          __syncwarp(0xff);
        }
        TS(22);
      }
    } else if (w == 2) {
      mbar_wait(bars + 8 * B_PREP, 0);
      flag_signal(g_cnt + C_PREP, 16, lane);
      TS(25);
      if (lane == 0) mbar_arrive(bars + 8 * B_USIG);
      mbar_wait(bars + 8 * B_ATTN, 0);
      if (lane == 0) {
        if (O_DEFER) mbar_wait(bars + 8 * (B_U + 3), 0);
        asm volatile("cp.async.bulk.global.shared::cta.bulk_group [%0], [%1], 20480;\ncp.async.bulk.commit_group;\n"
                     "cp.async.bulk.wait_group 0;\nfence.proxy.async.global;" ::"l"(g_O + b * 1280), "r"(sb + OFF_OA) : "memory");
      }
      TS(74);
      if (!(NOMB & 1)) flag_signal(g_cnt + C_O + 32 * b, 1, lane);
      else if (lane == 0) flag_bump(g_cnt + C_O + 32 * b);
      TS(26);
      if (lane == 0) mbar_arrive(bars + 8 * B_OSIG);

    } else {
      if (lane == 0) {
#pragma unroll 1
        for (int c = 0; c < 5; c++) {
          mbar_wait(bars + 8 * (B_YST + c), 0);
          asm volatile("cp.async.bulk.global.shared::cta.bulk_group [%0], [%1], 4096;\ncp.async.bulk.commit_group;"
                       ::"l"(g_Y + (5 * b + c) * Y_PITCH), "r"(sb + off_ch(c)) : "memory");
          if (c == 2) {
            asm volatile("cp.async.bulk.wait_group.read 0;" ::: "memory");
            mbar_arrive(bars + 8 * B_C34);
          }
        }
        asm volatile("cp.async.bulk.wait_group 0;\nfence.proxy.async.global;" ::: "memory");
        TS(75);
        if (!(NOMB & 2)) asm volatile("fence.release.gpu;" ::: "memory");
        flag_bump(g_cnt + C_Y + 32 * (b >> 4));
        TS(27);
        mbar_arrive(bars + 8 * B_YSIG);
        mbar_expect_tx(bars + 8 * B_YFULL, 20480);
        flag_wait(g_cnt + C_Y + 32 * hg, (lds32(sb + OFF_EPOCH) + 1) * 16);
        TS(24);
        tma_2d(sb + OFF_YT, &m.y, 128 * r, 80 * hg, bars + 8 * B_YFULL);
        tma_2d(sb + OFF_YT + 10240, &m.y, 128 * r + 64, 80 * hg, bars + 8 * B_YFULL);
      }
    }
  } else {
    asm volatile("setmaxnreg.inc.sync.aligned.u32 152;");
    if (wg < 2) {
      float acc[120];
#pragma unroll
      for (int i = 0; i < 120; i++) acc[i] = 0.f;
      const uint32_t da = desc_lo(sb + wg * 8192, 16), db = desc_lo(sb + ST_W, 8192), dc = desc_lo(sb + ST_WT, 2048);
      if (PW1) pin<120>(acc);
      if (PW1 == 2) mbar_wait(bars + 8 * B_FULL1, 0);
#pragma unroll 1
      for (int kb = 0; kb < 10; kb++) {
        mbar_wait(bars + 8 * (B_FULL1 + (kb & 3)), (kb >> 2) & 1);
        const uint32_t so = (kb & 3) * (STAGE_BYTES >> 4);
        wg_fence();
#pragma unroll
        for (int k = 0; k < 4; k++) {
          WgSST<192>::mma<HI_SW128, HI_SW128>(acc, da + so + 2 * k, db + so + 128 * k, 1);
          WgSST<48>::mma<HI_SW128, HI_SW32>(acc + 96, da + so + 2 * k, dc + so + 32 * k, 1);
        }
        wg_commit();
        wg_wait<1>();
        if (kb > 0 && lane == 0) mbar_arrive(bars + 8 * (kb == 4 ? B_E3 : B_EMPTY1 + ((kb - 1) & 3)));
      }
      mbar_wait(bars + 8 * B_EPOCH, 0);
      const uint32_t tag = lds32(sb + OFF_EPOCH) + 1;
      mbar_wait(bars + 8 * B_S3, 0);
      wg_wait<0>();
      pin<120>(acc);
      if (lane == 0) mbar_arrive(bars + 8 * B_P1);
      TSM(w == 0, 3 + wg);
      attention(acc, sb, b, wg, w, lane, tag);
    } else {
      const int tw = tid & 127, chl = 64 * (b & 1) + 8 * w + (lane >> 2);
      uint4* up = g_U + chl * U_PITCH + ((4 * (b >> 1) + (lane & 3)) ^ ((b >> 2) & 1));
      uint2 sw[10];
      uint32_t dv = 0;
      if (lane < 5) dv = __ldg(reinterpret_cast<const unsigned short*>(p.ssm_D) + 5 * b + lane);
#pragma unroll
      for (int i = 0; i < 10; i++) sw[i] = ldg64(reinterpret_cast<const uint2*>(p.shift_k) + chl + 128 * (i >> 1) + 32 * (i & 1));
      uint32_t tab[12];
      float tt[4];
      fft_tables(tab, tw);
      fft_twiddles(tt, tw);
      uint4 res[10];
#pragma unroll
      for (int i = 0; i < 10; i++) res[i] = make_uint4(0, 0, 0, 0);
#pragma unroll 1
      for (int slab = 0; slab < 5; slab++) {
#pragma unroll
        for (int i = 0; i < 8; i++) res[i] = res[i + 2];
        prep_slab(res + 8, sw, sb, slab, w, lane);
        TSIF(w == 0, 99 + 4 * slab);
#pragma unroll
        for (int i = 0; i < 8; i++) sw[i] = sw[i + 2];
      }
      TSIF(w == 0, 28);
      __syncwarp();
      if (lane == 0) mbar_arrive(bars + 8 * B_KVD + ((res[8].x ^ res[9].x) & p.zero));
      mbar_wait(bars + 8 * B_KVD, 0);
      fft_tables_store(tab, sb, tw);
      mbar_wait(bars + 8 * B_LAST, 0);
#pragma unroll
      for (int i = 0; i < 10; i++) up[(128 * (i >> 1) + 32 * (i & 1)) * U_PITCH] = res[i];
      __syncwarp();
      if (lane == 0) mbar_arrive(bars + 8 * B_PREP);
      TSIF(w == 0 && !U_TMA, 5);
      mbar_wait(bars + 8 * B_HB, 0);
      TSIF(w == 0, 2);
      const uint32_t ha = sb + U_BYTES + ((tw >> 3) * 16 + 8 + (tw & 7)) * 16;
      uint4 hv[5];
#pragma unroll
      for (int c = 0; c < 5; c++) hv[c] = lds128(ha + off_ch(c));
      __syncwarp();
#pragma unroll
      for (int c = 0; c < 5; c++) sts128((ha ^ 16) + off_ch(c), hv[c].x, hv[c].y, hv[c].z, hv[c].w);
      sts128(sb + OFF_TT + 16 * tw, __float_as_uint(tt[0]), __float_as_uint(tt[1]), __float_as_uint(tt[2]), __float_as_uint(tt[3]));
      if (tw < 5) asm volatile("st.shared.f32 [%0], %1;" ::"r"(sb + OFF_D + 4 * tw), "f"(bf_lo(dv) * 0.125f) : "memory");
      fence_async_smem();
      __syncwarp();
      if (lane == 0) mbar_arrive(bars + 8 * B_HA);
      TSIF(w == 0, 6);
    }

    FftConst fc;
    TSM(w == 0 && wg == 0, 104);
    mbar_wait(bars + 8 * B_HA, 0);
    fft_matrices(fc, sb, w, lane);
    TSM(w == 0 && wg == 0, 105);
    if (ATT_GATE && !H_EARLY) mbar_wait(bars + 8 * B_ATTN, 0);
    TSM(w == 0 && wg == 2, 124);
#pragma unroll 1
    for (uint32_t tasks = wg == 0 ? TASK0 : wg == 1 ? TASK1 : TASK2; tasks; tasks >>= 4) {
      const int c = (tasks & 7) - 1;
      conv_channel(fc, sb, c, wg, w, lane);
      if (lane == 0) mbar_arrive(bars + 8 * (B_YST + c));
      TSM(w == 0, 10 + c);
    }

    if (wg < 2) {
      const int g = lane >> 2;
      float acc[40];
#pragma unroll
      for (int i = 0; i < 40; i++) acc[i] = 0.f;
      const uint32_t da = desc_lo(sb + wg * 1024, 2048), db = desc_lo(sb, 2560);
      mbar_wait(bars + 8 * B_ATTN, 0);
      mbar_wait(bars + 8 * (B_YST + 3), 0);
      mbar_wait(bars + 8 * (B_YST + 4), 0);
      if (PW2) mbar_wait(bars + 8 * B_FULL2, 0);
      TSM(w == 0, 15 + wg);
#pragma unroll 1
      for (int j = 0; j < 8; j++) {
        mbar_wait(bars + 8 * (B_FULL2 + j), 0);
        const uint32_t oa = da + (off_o(j) >> 4), ob = db + (off_w(j) >> 4);
        wg_fence();
#pragma unroll
        for (int k = 0; k < 5; k++) WgSST<80>::mma<HI_NONE, HI_SW32>(acc, oa + 256 * k, ob + 32 * k, 1);
        wg_commit();
        wg_wait<1>();
        if (j >= 1 && j <= 4 && lane == 0) mbar_arrive(bars + 8 * (B_EMPTY2 + j - 1));
      }
      TSIF(w == 0 && wg == 0, 113);
      const int tr = 64 * wg + 16 * w + (lane & 15);
      const uint32_t fm = sb + OFF_QS + tr * 128, fx = (lane >> 4) ^ (tr & 7);
      const uint32_t ft = sb + OFF_QT + tr * 32 + (((lane >> 4) ^ (tr >> 2)) & 1) * 16;
      const float g0 = __uint_as_float(lds32(sb + OFF_GATE + (64 * wg + 16 * w + g) * 4));
      const float g1 = __uint_as_float(lds32(sb + OFF_GATE + (64 * wg + 16 * w + 8 + g) * 4));
      const uint32_t ga = pack2(g0, g0), gb = pack2(g1, g1);
      const uint32_t na = pack2(1.f - g0, 1.f - g0), nb = pack2(1.f - g1, 1.f - g1);

      wg_wait<0>();
      pin<40>(acc);
      TSM(w == 0, 17 + wg);
      uint32_t pb[20];
#pragma unroll
      for (int j = 0; j < 10; j++) {
        pb[2 * j] = bmul(na, pack2(acc[4 * j], acc[4 * j + 1]));
        pb[2 * j + 1] = bmul(nb, pack2(acc[4 * j + 2], acc[4 * j + 3]));
        asm volatile("" : "+r"(pb[2 * j]), "+r"(pb[2 * j + 1]));
      }
      const uint32_t ya = sb + OFF_YT + wg * 10240 + ((lane >> 4) * 8 + (lane & 7)) * 128 +
                          (((2 * w + (((lane >> 3) & 1) ^ wg)) ^ (lane & 7)) << 4);
      uint32_t qf[20];
      mbar_wait(bars + 8 * B_QF, 0);
#pragma unroll
      for (int j = 0; j < 5; j++) ldsm4(qf + 4 * j, j < 4 ? fm + ((fx ^ (2 * j)) << 4) : ft);
      mbar_wait(bars + 8 * B_YFULL, 0);
      TSM(w == 0 && wg == 0, 19);
#pragma unroll
      for (int j = 0; j < 5; j++) {
        uint32_t y[4];
        ldsm4t(y, ya + 2048 * j);
#pragma unroll
        for (int i = 0; i < 4; i++) qf[4 * j + i] = badd(bmul((i & 1) ? gb : ga, bmul(qf[4 * j + i], y[i])), pb[4 * j + i]);
      }
#pragma unroll
      for (int j = 0; j < 5; j++) stsm4(j < 4 ? fm + ((fx ^ (2 * j)) << 4) : ft, qf + 4 * j);
      fence_async_smem();
      __syncwarp();
      if (lane == 0) {
        const int row = 64 * wg + 16 * w;
        asm volatile("cp.async.bulk.tensor.2d.global.shared::cta.bulk_group [%0, {%2, %3}], [%1];"
                     ::"l"(&m.om), "r"(sb + OFF_QS + row * 128), "r"(80 * hg), "r"(128 * r + row) : "memory");
        asm volatile("cp.async.bulk.tensor.2d.global.shared::cta.bulk_group [%0, {%2, %3}], [%1];"
                     ::"l"(&m.ot), "r"(sb + OFF_QT + row * 32), "r"(80 * hg + 64), "r"(128 * r + row) : "memory");
        asm volatile("cp.async.bulk.commit_group;\ncp.async.bulk.wait_group.read 0;" ::: "memory");
      }
      TSM(true, 40 + 4 * wg + w);
      if (ENDBAR) asm volatile("bar.sync 15, 256;" ::: "memory");
    }
  }
}

typedef CUresult (*EncodeFn)(CUtensorMap*, CUtensorMapDataType, cuuint32_t, void*, const cuuint64_t*, const cuuint64_t*,
                             const cuuint32_t*, const cuuint32_t*, CUtensorMapInterleave, CUtensorMapSwizzle,
                             CUtensorMapL2promotion, CUtensorMapFloatOOBfill);

void encode(EncodeFn fn, CUtensorMap* tm, const void* base, int rank, const cuuint64_t* dims, const cuuint64_t* strides,
            const cuuint32_t* box, CUtensorMapSwizzle swz) {
  const cuuint32_t ones[3] = {1, 1, 1};
  fn(tm, CU_TENSOR_MAP_DATA_TYPE_BFLOAT16, rank, const_cast<void*>(base), dims, strides, box, ones,
     CU_TENSOR_MAP_INTERLEAVE_NONE, swz, CU_TENSOR_MAP_L2_PROMOTION_L2_128B, CU_TENSOR_MAP_FLOAT_OOB_FILL_NONE);
}

}

extern "C" void kernel_launch(void* const* d_in, const int* in_sizes, int n_in, void* d_out, int out_size) {
  (void)in_sizes; (void)n_in; (void)out_size;
  Params p;
  p.q = (const __nv_bfloat16*)d_in[0];
  p.k = (const __nv_bfloat16*)d_in[1];
  p.v = (const __nv_bfloat16*)d_in[2];
  p.shift_k = (const __nv_bfloat16*)d_in[3];
  p.ssm_k = (const __nv_bfloat16*)d_in[4];
  p.ssm_D = (const __nv_bfloat16*)d_in[5];
  p.wqkv = (const __nv_bfloat16*)d_in[7];
  p.wo = (const __nv_bfloat16*)d_in[8];
  p.gate_w = (const __nv_bfloat16*)d_in[9];
  p.out = (__nv_bfloat16*)d_out;
  p.zero = 0;

  static EncodeFn fn = nullptr;
  static void *yaddr = nullptr, *uaddr = nullptr;
  if (!fn) {
    cudaDriverEntryPointQueryResult qr;
    void* f = nullptr;
    cudaGetDriverEntryPoint("cuTensorMapEncodeTiled", &f, cudaEnableDefault, &qr);
    fn = (EncodeFn)f;
    cudaGetSymbolAddress(&yaddr, g_Y);
    cudaGetSymbolAddress(&uaddr, g_U);
    cudaFuncSetAttribute(fused_kernel, cudaFuncAttributeMaxDynamicSharedMemorySize, SMEM_BYTES);
  }
  Maps m;
  {
    const cuuint64_t dims[3] = {640, 1024, 2}, st[2] = {2560, 1280};
    const cuuint32_t box[3] = {64, 64, 2};
    encode(fn, &m.x, p.q, 3, dims, st, box, CU_TENSOR_MAP_SWIZZLE_128B);
  }
  {
    const cuuint64_t dims[3] = {640, 640, 3}, st[2] = {3840, 1280};
    const cuuint32_t box[3] = {64, 64, 3}, boxt[3] = {16, 64, 3};
    encode(fn, &m.wm, p.wqkv, 3, dims, st, box, CU_TENSOR_MAP_SWIZZLE_128B);
    encode(fn, &m.wt, p.wqkv, 3, dims, st, boxt, CU_TENSOR_MAP_SWIZZLE_32B);
  }
  {
    const cuuint64_t dims[3] = {64, 2048, 10}, st[2] = {1280, 128};
    const cuuint32_t boxk[3] = {64, 35, 1}, boxv[3] = {64, 32, 1};
    encode(fn, &m.k, p.k, 3, dims, st, boxk, CU_TENSOR_MAP_SWIZZLE_128B);
    encode(fn, &m.v, p.v, 3, dims, st, boxv, CU_TENSOR_MAP_SWIZZLE_128B);
  }
  {
    const cuuint64_t dims[2] = {2048, 640}, st[1] = {Y_PITCH * 16};
    const cuuint32_t box[2] = {64, 80};
    encode(fn, &m.y, yaddr, 2, dims, st, box, CU_TENSOR_MAP_SWIZZLE_128B);
    const cuuint64_t stu[1] = {U_PITCH * 16};
    const cuuint32_t boxu[2] = {32, 64};
    encode(fn, &m.u, uaddr, 2, dims, stu, boxu, CU_TENSOR_MAP_SWIZZLE_NONE);
  }
  {
    const cuuint64_t dims[2] = {640, 2048}, st[1] = {1280};
    const cuuint32_t bqm[2] = {64, 128}, bqt[2] = {16, 128}, bom[2] = {64, 16}, bot[2] = {16, 16};
    encode(fn, &m.qm, p.q, 2, dims, st, bqm, CU_TENSOR_MAP_SWIZZLE_128B);
    encode(fn, &m.qt, p.q, 2, dims, st, bqt, CU_TENSOR_MAP_SWIZZLE_32B);
    encode(fn, &m.om, p.out, 2, dims, st, bom, CU_TENSOR_MAP_SWIZZLE_128B);
    encode(fn, &m.ot, p.out, 2, dims, st, bot, CU_TENSOR_MAP_SWIZZLE_32B);
  }
  fused_kernel<<<NCTA + NHELP, NTHR, SMEM_BYTES>>>(m, p);
}
```

```cpp
#include <cuda.h>
#include <cuda_bf16.h>
#include <cuda_runtime.h>
#include <stdint.h>

namespace {

constexpr int SEQ = 2048, DIM = 640, NCTA = 128, NTHR = 512;

#define TRIG_KB 9
#define KV_KB 2
#define DEV_EXIT 0
#define ATT_GATE 1
#define G_AFTER 0
#define FENCE_LO 0
#define FENCE_HI 0
#define PW1 2
#define PW2 1
#define ENDBAR 0
#define PAD_KB 0
#define Y_ALIAS 1
#define H_EARLY 1
#define NOMB 0
#define SRC_ROT 0
#define WAIT_NS 0
#define WB_TRIG B_USIG
#define G_POS 0
#define TAILF 1
#define T_ISSUE 384
#define T_PF 416
#define T_INIT 448
#define ATT_MERGE 0
#define BMAP 1
#define PRE2 1
#define KV_MIX 0
#define O_DEFER 0
#define TASK0 0x52
#define TASK1 0x3
#define TASK2 0x41
#define HALO_FIRST 1
#define PREV_EARLY 0
#define SKIP 0
#define ACQ 0
#define U_TMA 0
#define U_GATE 0
#define RF_GATE 0
#define WO_TRIG B_WST
#define WL_TRIG B_WOP
#define WO_GATE 1

constexpr uint32_t STAGE_BYTES = 47104, ST_W = 16384, ST_WT = 40960;
constexpr uint32_t O_BYTES = 20480, WO_BYTES = 12800;
constexpr uint32_t OFF_OA = 0;
constexpr uint32_t OFF_QS = 3 * O_BYTES, OFF_QT = OFF_QS + 16384;
constexpr uint32_t OFF_WC = 81920;
constexpr uint32_t OFF_WA = 94720;
constexpr uint32_t OFF_GATE = 145920;
constexpr uint32_t OFF_TT = 146432;
constexpr uint32_t OFF_KVX = 148480;
constexpr uint32_t OFF_CH3 = 163840;
constexpr uint32_t CH_BYTES = 12288, U_BYTES = 4096;
constexpr uint32_t OFF_FT = 225280, OFF_GT = 229376;
constexpr uint32_t OFF_CH0 = 188416;
constexpr uint32_t OFF_KVS = OFF_CH0, KVS_V = 4480, KVS_BYTES = 8576;
constexpr uint32_t OFF_WS = OFF_WA;
__device__ __forceinline__ uint32_t off_us(int s) { return OFF_CH0 + 4096 * ((0x65320 >> (4 * s)) & 7); }
constexpr uint32_t OFF_YT = 163840;
constexpr uint32_t OFF_BAR = 231936;
constexpr uint32_t SMEM_BYTES = OFF_BAR + 512;

enum : uint32_t {
  B_FULL1 = 0, B_EMPTY1 = 4, B_S3 = 7, B_FULL2 = 52, B_EMPTY2 = 13, B_U = 8, B_GATE = 12, B_HA = 19, B_HB = 20,
  B_ATTN = 21, B_C34 = 22, B_CONV = 23, B_YFULL = 24, B_EPOCH = 25, B_PREP = 26, B_P1 = 27, B_LAST = 28,
  B_E3 = 29, B_OSIG = 30, B_WOP = 31, B_USIG = 32, B_WST = 33, B_KV = 34, B_KVD = 39, B_QF = 17, B_YST = 40,
  B_US = 45, B_YSIG = 50
};
constexpr uint32_t OFF_EPOCH = OFF_BAR + 8 * 51, OFF_D = OFF_BAR + 8 * 60;
__device__ __forceinline__ uint32_t off_o(int j) { return j < 4 ? OFF_OA + j * O_BYTES : j < 6 ? OFF_CH0 + (j - 4) * O_BYTES : OFF_OA + (j - 6) * O_BYTES; }
__device__ __forceinline__ uint32_t off_w(int j) { return j < 4 ? OFF_WA + j * WO_BYTES : j == 4 ? OFF_KVX : j == 5 ? OFF_WC : OFF_WA + (j - 6) * WO_BYTES; }
__device__ __forceinline__ int step_src(int hg, int j) { return SRC_ROT ? (hg + j) & 7 : j == 0 ? hg : j <= hg ? j - 1 : j; }
__device__ __forceinline__ bool tail_first(int hg) { return TAILF && (hg & 3) == 3; }
__device__ __forceinline__ uint32_t off_ch(int c) { return (c < 3 ? OFF_CH0 : OFF_CH3 - 3 * CH_BYTES) + c * CH_BYTES; }

#define U_PITCH 264
__device__ __align__(1024) uint4 g_U[DIM * U_PITCH];
__device__ uint4 g_O[NCTA * 1280];
#define g_Y g_U
constexpr int Y_PITCH = U_PITCH;
__device__ uint4 g_WO[64 * 800];
__device__ uint4 g_halo[NCTA * 2 * 7 * 32];
__device__ float g_gate[SEQ + PAD_KB * 256];
__device__ unsigned g_cnt[32 * (1 + 2 * 16 + 8 + NCTA)];
constexpr int C_LAUNCH = 0, C_PREP = 32, C_Y = 32 * 17, C_W = 32 * 33, C_O = 32 * 41;

#define TSM(cond, slot) do { } while (0)
#define TSIF(cond, slot) do { if (__LINE__ >= FENCE_LO && __LINE__ < FENCE_HI) sched_fence(); } while (0)
__device__ __forceinline__ void sched_fence() {
  asm volatile("{\n.reg .pred p;\n.reg .u32 c;\nmov.u32 c, %%clock;\nsetp.eq.u32 p, c, 0;\n@p st.shared.u32 [%0], c;\n}"
               ::"r"(1024 + OFF_EPOCH + 4) : "memory");
}
#define TS(slot) TSIF(true, slot)

struct Params {
  const __nv_bfloat16 *q, *k, *v, *shift_k, *ssm_k, *ssm_D, *wqkv, *wo, *gate_w;
  __nv_bfloat16* out;
  uint32_t zero;
};

#define POLL_NS 0
constexpr int SPIN_LIMIT = 1 << 17;

__device__ __forceinline__ void mbar_init(uint32_t bar, uint32_t count) {
  asm volatile("mbarrier.init.shared::cta.b64 [%0], %1;" ::"r"(bar), "r"(count) : "memory");
}
__device__ __forceinline__ void mbar_expect_tx(uint32_t bar, uint32_t bytes) {
  asm volatile("mbarrier.arrive.expect_tx.shared::cta.b64 _, [%0], %1;" ::"r"(bar), "r"(bytes) : "memory");
}
__device__ __forceinline__ void mbar_arrive(uint32_t bar) {
  asm volatile("mbarrier.arrive.shared::cta.b64 _, [%0];" ::"r"(bar) : "memory");
}
__device__ __forceinline__ void mbar_wait(uint32_t bar, uint32_t parity) {
  uint32_t ok;
  int spins = 0;
  do {
    if (WAIT_NS)
      asm volatile("{\n.reg .pred p;\nmbarrier.try_wait.parity.shared::cta.b64 p, [%1], %2, %3;\nselp.b32 %0, 1, 0, p;\n}"
                   : "=r"(ok) : "r"(bar), "r"(parity), "r"(WAIT_NS) : "memory");
    else
      asm volatile("{\n.reg .pred p;\nmbarrier.try_wait.parity.shared::cta.b64 p, [%1], %2;\nselp.b32 %0, 1, 0, p;\n}"
                   : "=r"(ok) : "r"(bar), "r"(parity) : "memory");
    if (++spins > SPIN_LIMIT) break;
  } while (!ok);
}
__device__ __forceinline__ unsigned flag_read(const unsigned* p) {
  unsigned v;
  asm volatile("ld.relaxed.gpu.global.u32 %0, [%1];" : "=r"(v) : "l"(p) : "memory");
  return v;
}
__device__ __forceinline__ void flag_poll(const unsigned* p, unsigned target) {
  unsigned v;
  int spins = 0;
  do {
    if (POLL_NS && spins) __nanosleep(POLL_NS);
    asm volatile("ld.relaxed.gpu.global.u32 %0, [%1];" : "=r"(v) : "l"(p) : "memory");
    if (++spins > SPIN_LIMIT) break;
  } while ((int)(v - target) < 0);
}
__device__ __forceinline__ void flag_wait(const unsigned* p, unsigned target) {
  flag_poll(p, target);
  if (ACQ) asm volatile("fence.acquire.gpu;\nfence.proxy.async.global;" ::: "memory");
}
__device__ __forceinline__ void flag_signal(unsigned* p, int n, int lane) {
  if (lane == 0) asm volatile("fence.release.gpu;" ::: "memory");
  __syncwarp();
  if (lane < n) asm volatile("red.relaxed.gpu.global.add.u32 [%0], 1;" ::"l"(p + 32 * lane) : "memory");
}
__device__ __forceinline__ void flag_bump(unsigned* p) {
  asm volatile("red.relaxed.gpu.global.add.u32 [%0], 1;" ::"l"(p) : "memory");
}
__device__ __forceinline__ void fence_async_smem() { asm volatile("fence.proxy.async.shared::cta;" ::: "memory"); }
__device__ __forceinline__ void wg_sync(int id) { asm volatile("bar.sync %0, 128;" ::"r"(id) : "memory"); }

__device__ __forceinline__ void tma_2d(uint32_t dst, const CUtensorMap* tm, int c0, int c1, uint32_t bar) {
  asm volatile("cp.async.bulk.tensor.2d.shared::cluster.global.mbarrier::complete_tx::bytes [%0], [%1, {%3, %4}], [%2];"
               ::"r"(dst), "l"(tm), "r"(bar), "r"(c0), "r"(c1) : "memory");
}
__device__ __forceinline__ void tma_3d(uint32_t dst, const CUtensorMap* tm, int c0, int c1, int c2, uint32_t bar) {
  asm volatile("cp.async.bulk.tensor.3d.shared::cluster.global.mbarrier::complete_tx::bytes [%0], [%1, {%3, %4, %5}], [%2];"
               ::"r"(dst), "l"(tm), "r"(bar), "r"(c0), "r"(c1), "r"(c2) : "memory");
}
__device__ __forceinline__ void bulk_load(uint32_t dst, const void* src, uint32_t bytes, uint32_t bar) {
  asm volatile("cp.async.bulk.shared::cluster.global.mbarrier::complete_tx::bytes [%0], [%1], %2, [%3];"
               ::"r"(dst), "l"(src), "r"(bytes), "r"(bar) : "memory");
}
__device__ __forceinline__ void tm_prefetch(const CUtensorMap* tm) {
  asm volatile("prefetch.tensormap [%0];" ::"l"(tm) : "memory");
}

__device__ __forceinline__ void wg_fence() { asm volatile("wgmma.fence.sync.aligned;" ::: "memory"); }
__device__ __forceinline__ void wg_commit() { asm volatile("wgmma.commit_group.sync.aligned;" ::: "memory"); }
template <int N> __device__ __forceinline__ void wg_wait() { asm volatile("wgmma.wait_group.sync.aligned %0;" ::"n"(N) : "memory"); }
__device__ __forceinline__ uint32_t desc_lo(uint32_t addr, uint32_t lbo) { return ((addr & 0x3FFFF) >> 4) | ((lbo >> 4) << 16); }
constexpr uint32_t desc_hi(uint32_t sbo, uint32_t swz) { return (sbo >> 4) | (swz << 30); }
constexpr uint32_t HI_SW128 = desc_hi(1024, 1), HI_SW64 = desc_hi(512, 2), HI_SW32 = desc_hi(256, 3), HI_NONE = desc_hi(128, 0);
template <int N> __device__ __forceinline__ void pin(float* d) {
#pragma unroll
  for (int i = 0; i < N; i++) asm volatile("" : "+f"(d[i])::"memory");
}

__device__ __forceinline__ uint32_t lds32(uint32_t a) {
  uint32_t v;
  asm volatile("ld.volatile.shared.u32 %0, [%1];" : "=r"(v) : "r"(a) : "memory");
  return v;
}
__device__ __forceinline__ uint4 ldg128(const void* a) {
  uint4 v;
  asm volatile("ld.global.nc.v4.u32 {%0, %1, %2, %3}, [%4];" : "=r"(v.x), "=r"(v.y), "=r"(v.z), "=r"(v.w) : "l"(a) : "memory");
  return v;
}
__device__ __forceinline__ uint2 ldg64(const void* a) {
  uint2 v;
  asm volatile("ld.global.nc.v2.u32 {%0, %1}, [%2];" : "=r"(v.x), "=r"(v.y) : "l"(a) : "memory");
  return v;
}
__device__ __forceinline__ void ldsm4(uint32_t* r, uint32_t a) {
  asm volatile("ldmatrix.sync.aligned.m8n8.x4.shared.b16 {%0, %1, %2, %3}, [%4];"
               : "=r"(r[0]), "=r"(r[1]), "=r"(r[2]), "=r"(r[3]) : "r"(a) : "memory");
}
__device__ __forceinline__ void ldsm4t(uint32_t* r, uint32_t a) {
  asm volatile("ldmatrix.sync.aligned.m8n8.x4.trans.shared.b16 {%0, %1, %2, %3}, [%4];"
               : "=r"(r[0]), "=r"(r[1]), "=r"(r[2]), "=r"(r[3]) : "r"(a) : "memory");
}
__device__ __forceinline__ uint4 lds128(uint32_t a) {
  uint4 v;
  asm volatile("ld.shared.v4.u32 {%0, %1, %2, %3}, [%4];" : "=r"(v.x), "=r"(v.y), "=r"(v.z), "=r"(v.w) : "r"(a) : "memory");
  return v;
}
__device__ __forceinline__ void sts128(uint32_t a, uint32_t x, uint32_t y, uint32_t z, uint32_t w) {
  asm volatile("st.shared.v4.u32 [%0], {%1, %2, %3, %4};" ::"r"(a), "r"(x), "r"(y), "r"(z), "r"(w) : "memory");
}
__device__ __forceinline__ void stsm4(uint32_t a, const uint32_t* r) {
  asm volatile("stmatrix.sync.aligned.m8n8.x4.shared.b16 [%0], {%1, %2, %3, %4};" ::"r"(a), "r"(r[0]), "r"(r[1]), "r"(r[2]), "r"(r[3]) : "memory");
}
__device__ __forceinline__ void stsm4t(uint32_t a, const uint32_t* r) {
  asm volatile("stmatrix.sync.aligned.m8n8.x4.trans.shared.b16 [%0], {%1, %2, %3, %4};" ::"r"(a), "r"(r[0]), "r"(r[1]), "r"(r[2]), "r"(r[3]) : "memory");
}
__device__ __forceinline__ uint32_t pack2(float lo, float hi) {
  uint32_t r;
  asm("cvt.rn.bf16x2.f32 %0, %1, %2;" : "=r"(r) : "f"(hi), "f"(lo));
  return r;
}
__device__ __forceinline__ uint32_t movm(uint32_t a) {
  uint32_t d;
  asm volatile("movmatrix.sync.aligned.m8n8.trans.b16 %0, %1;" : "=r"(d) : "r"(a));
  return d;
}
__device__ __forceinline__ uint32_t bmul(uint32_t a, uint32_t b) {
  uint32_t d;
  asm("mul.rn.bf16x2 %0, %1, %2;" : "=r"(d) : "r"(a), "r"(b));
  return d;
}
__device__ __forceinline__ uint32_t badd(uint32_t a, uint32_t b) {
  uint32_t d;
  asm("add.rn.bf16x2 %0, %1, %2;" : "=r"(d) : "r"(a), "r"(b));
  return d;
}
__device__ __forceinline__ float bf_lo(uint32_t x) { return __uint_as_float(x << 16); }
__device__ __forceinline__ float bf_hi(uint32_t x) { return __uint_as_float(x & 0xFFFF0000u); }
__device__ __forceinline__ float ex2(float x) {
  float y;
  asm("ex2.approx.ftz.f32 %0, %1;" : "=f"(y) : "f"(x));
  return y;
}
__device__ __forceinline__ float rcp(float x) {
  float y;
  asm("rcp.approx.ftz.f32 %0, %1;" : "=f"(y) : "f"(x));
  return y;
}
__device__ __forceinline__ void mma16816(float* d, uint32_t a0, uint32_t a1, uint32_t a2, uint32_t a3, uint32_t b0, uint32_t b1) {
  asm volatile("mma.sync.aligned.m16n8k16.row.col.f32.bf16.bf16.f32 {%0, %1, %2, %3}, {%4, %5, %6, %7}, {%8, %9}, {%0, %1, %2, %3};"
               : "+f"(d[0]), "+f"(d[1]), "+f"(d[2]), "+f"(d[3])
               : "r"(a0), "r"(a1), "r"(a2), "r"(a3), "r"(b0), "r"(b1));
}
__device__ __forceinline__ void mma1688(float* d, uint32_t a0, uint32_t a1, uint32_t b0) {
  asm volatile("mma.sync.aligned.m16n8k8.row.col.f32.bf16.bf16.f32 {%0, %1, %2, %3}, {%4, %5}, {%6}, {%0, %1, %2, %3};"
               : "+f"(d[0]), "+f"(d[1]), "+f"(d[2]), "+f"(d[3])
               : "r"(a0), "r"(a1), "r"(b0));
}

template <int N> struct WgRS;
template <int N> struct WgSST;
template <> struct WgRS<32> {
  template <uint32_t HB>
  static __device__ __forceinline__ void mma(float* d, const uint32_t* a, uint32_t db) {
    asm volatile("{\n.reg .pred p;\n.reg .b64 db;\nsetp.ne.b32 p, %22, 0;\n"
      "mov.b64 db, {%20, %21};\n"
      "wgmma.mma_async.sync.aligned.m64n32k16.f32.bf16.bf16 {"
      "%0, %1, %2, %3, %4, %5, %6, %7, %8, %9, %10, %11, %12, %13, %14, %15"
      "}, {%16, %17, %18, %19}, db, p, 1, 1, 1;\n}\n"
      : "+f"(d[0]), "+f"(d[1]), "+f"(d[2]), "+f"(d[3]), "+f"(d[4]), "+f"(d[5]), "+f"(d[6]), "+f"(d[7]),
        "+f"(d[8]), "+f"(d[9]), "+f"(d[10]), "+f"(d[11]), "+f"(d[12]), "+f"(d[13]), "+f"(d[14]), "+f"(d[15])
      : "r"(a[0]), "r"(a[1]), "r"(a[2]), "r"(a[3]), "r"(db), "n"(HB), "n"(1));
  }
  template <uint32_t HB>
  static __device__ __forceinline__ void set(float* d, const uint32_t* a, uint32_t db) {
    asm volatile("{\n.reg .pred p;\n.reg .b64 db;\nsetp.ne.b32 p, %22, 0;\n"
      "mov.b64 db, {%20, %21};\n"
      "wgmma.mma_async.sync.aligned.m64n32k16.f32.bf16.bf16 {"
      "%0, %1, %2, %3, %4, %5, %6, %7, %8, %9, %10, %11, %12, %13, %14, %15"
      "}, {%16, %17, %18, %19}, db, p, 1, 1, 1;\n}\n"
      : "=f"(d[0]), "=f"(d[1]), "=f"(d[2]), "=f"(d[3]), "=f"(d[4]), "=f"(d[5]), "=f"(d[6]), "=f"(d[7]),
        "=f"(d[8]), "=f"(d[9]), "=f"(d[10]), "=f"(d[11]), "=f"(d[12]), "=f"(d[13]), "=f"(d[14]), "=f"(d[15])
      : "r"(a[0]), "r"(a[1]), "r"(a[2]), "r"(a[3]), "r"(db), "n"(HB), "n"(0));
  }
};
template <> struct WgRS<64> {
  template <uint32_t HB>
  static __device__ __forceinline__ void mma(float* d, const uint32_t* a, uint32_t db) {
    asm volatile("{\n.reg .pred p;\n.reg .b64 db;\nsetp.ne.b32 p, %38, 0;\n"
      "mov.b64 db, {%36, %37};\n"
      "wgmma.mma_async.sync.aligned.m64n64k16.f32.bf16.bf16 {"
      "%0, %1, %2, %3, %4, %5, %6, %7, %8, %9, %10, %11, %12, %13, %14, %15, "
      "%16, %17, %18, %19, %20, %21, %22, %23, %24, %25, %26, %27, %28, %29, %30, %31"
      "}, {%32, %33, %34, %35}, db, p, 1, 1, 1;\n}\n"
      : "+f"(d[0]), "+f"(d[1]), "+f"(d[2]), "+f"(d[3]), "+f"(d[4]), "+f"(d[5]), "+f"(d[6]), "+f"(d[7]),
        "+f"(d[8]), "+f"(d[9]), "+f"(d[10]), "+f"(d[11]), "+f"(d[12]), "+f"(d[13]), "+f"(d[14]), "+f"(d[15]),
        "+f"(d[16]), "+f"(d[17]), "+f"(d[18]), "+f"(d[19]), "+f"(d[20]), "+f"(d[21]), "+f"(d[22]), "+f"(d[23]),
        "+f"(d[24]), "+f"(d[25]), "+f"(d[26]), "+f"(d[27]), "+f"(d[28]), "+f"(d[29]), "+f"(d[30]), "+f"(d[31])
      : "r"(a[0]), "r"(a[1]), "r"(a[2]), "r"(a[3]), "r"(db), "n"(HB), "n"(1));
  }
  template <uint32_t HB>
  static __device__ __forceinline__ void set(float* d, const uint32_t* a, uint32_t db) {
    asm volatile("{\n.reg .pred p;\n.reg .b64 db;\nsetp.ne.b32 p, %38, 0;\n"
      "mov.b64 db, {%36, %37};\n"
      "wgmma.mma_async.sync.aligned.m64n64k16.f32.bf16.bf16 {"
      "%0, %1, %2, %3, %4, %5, %6, %7, %8, %9, %10, %11, %12, %13, %14, %15, "
      "%16, %17, %18, %19, %20, %21, %22, %23, %24, %25, %26, %27, %28, %29, %30, %31"
      "}, {%32, %33, %34, %35}, db, p, 1, 1, 1;\n}\n"
      : "=f"(d[0]), "=f"(d[1]), "=f"(d[2]), "=f"(d[3]), "=f"(d[4]), "=f"(d[5]), "=f"(d[6]), "=f"(d[7]),
        "=f"(d[8]), "=f"(d[9]), "=f"(d[10]), "=f"(d[11]), "=f"(d[12]), "=f"(d[13]), "=f"(d[14]), "=f"(d[15]),
        "=f"(d[16]), "=f"(d[17]), "=f"(d[18]), "=f"(d[19]), "=f"(d[20]), "=f"(d[21]), "=f"(d[22]), "=f"(d[23]),
        "=f"(d[24]), "=f"(d[25]), "=f"(d[26]), "=f"(d[27]), "=f"(d[28]), "=f"(d[29]), "=f"(d[30]), "=f"(d[31])
      : "r"(a[0]), "r"(a[1]), "r"(a[2]), "r"(a[3]), "r"(db), "n"(HB), "n"(0));
  }
};
template <> struct WgSST<48> {
  template <uint32_t HA, uint32_t HB>
  static __device__ __forceinline__ void mma(float* d, uint32_t da, uint32_t db, int sc) {
    asm volatile("{\n.reg .pred p;\n.reg .b64 da, db;\nsetp.ne.b32 p, %28, 0;\n"
      "mov.b64 da, {%24, %25};\nmov.b64 db, {%26, %27};\n"
      "wgmma.mma_async.sync.aligned.m64n48k16.f32.bf16.bf16 {"
      "%0, %1, %2, %3, %4, %5, %6, %7, %8, %9, %10, %11, %12, %13, %14, %15, "
      "%16, %17, %18, %19, %20, %21, %22, %23"
      "}, da, db, p, 1, 1, 0, 1;\n}\n"
      : "+f"(d[0]), "+f"(d[1]), "+f"(d[2]), "+f"(d[3]), "+f"(d[4]), "+f"(d[5]), "+f"(d[6]), "+f"(d[7]),
        "+f"(d[8]), "+f"(d[9]), "+f"(d[10]), "+f"(d[11]), "+f"(d[12]), "+f"(d[13]), "+f"(d[14]), "+f"(d[15]),
        "+f"(d[16]), "+f"(d[17]), "+f"(d[18]), "+f"(d[19]), "+f"(d[20]), "+f"(d[21]), "+f"(d[22]), "+f"(d[23])
      : "r"(da), "n"(HA), "r"(db), "n"(HB), "r"(sc));
  }
};
template <> struct WgSST<80> {
  template <uint32_t HA, uint32_t HB>
  static __device__ __forceinline__ void mma(float* d, uint32_t da, uint32_t db, int sc) {
    asm volatile("{\n.reg .pred p;\n.reg .b64 da, db;\nsetp.ne.b32 p, %44, 0;\n"
      "mov.b64 da, {%40, %41};\nmov.b64 db, {%42, %43};\n"
      "wgmma.mma_async.sync.aligned.m64n80k16.f32.bf16.bf16 {"
      "%0, %1, %2, %3, %4, %5, %6, %7, %8, %9, %10, %11, %12, %13, %14, %15, "
      "%16, %17, %18, %19, %20, %21, %22, %23, %24, %25, %26, %27, %28, %29, %30, %31, "
      "%32, %33, %34, %35, %36, %37, %38, %39"
      "}, da, db, p, 1, 1, 0, 1;\n}\n"
      : "+f"(d[0]), "+f"(d[1]), "+f"(d[2]), "+f"(d[3]), "+f"(d[4]), "+f"(d[5]), "+f"(d[6]), "+f"(d[7]),
        "+f"(d[8]), "+f"(d[9]), "+f"(d[10]), "+f"(d[11]), "+f"(d[12]), "+f"(d[13]), "+f"(d[14]), "+f"(d[15]),
        "+f"(d[16]), "+f"(d[17]), "+f"(d[18]), "+f"(d[19]), "+f"(d[20]), "+f"(d[21]), "+f"(d[22]), "+f"(d[23]),
        "+f"(d[24]), "+f"(d[25]), "+f"(d[26]), "+f"(d[27]), "+f"(d[28]), "+f"(d[29]), "+f"(d[30]), "+f"(d[31]),
        "+f"(d[32]), "+f"(d[33]), "+f"(d[34]), "+f"(d[35]), "+f"(d[36]), "+f"(d[37]), "+f"(d[38]), "+f"(d[39])
      : "r"(da), "n"(HA), "r"(db), "n"(HB), "r"(sc));
  }
};
template <> struct WgSST<192> {
  template <uint32_t HA, uint32_t HB>
  static __device__ __forceinline__ void mma(float* d, uint32_t da, uint32_t db, int sc) {
    asm volatile("{\n.reg .pred p;\n.reg .b64 da, db;\nsetp.ne.b32 p, %100, 0;\n"
      "mov.b64 da, {%96, %97};\nmov.b64 db, {%98, %99};\n"
      "wgmma.mma_async.sync.aligned.m64n192k16.f32.bf16.bf16 {"
      "%0, %1, %2, %3, %4, %5, %6, %7, %8, %9, %10, %11, %12, %13, %14, %15, "
      "%16, %17, %18, %19, %20, %21, %22, %23, %24, %25, %26, %27, %28, %29, %30, %31, "
      "%32, %33, %34, %35, %36, %37, %38, %39, %40, %41, %42, %43, %44, %45, %46, %47, "
      "%48, %49, %50, %51, %52, %53, %54, %55, %56, %57, %58, %59, %60, %61, %62, %63, "
      "%64, %65, %66, %67, %68, %69, %70, %71, %72, %73, %74, %75, %76, %77, %78, %79, "
      "%80, %81, %82, %83, %84, %85, %86, %87, %88, %89, %90, %91, %92, %93, %94, %95"
      "}, da, db, p, 1, 1, 0, 1;\n}\n"
      : "+f"(d[0]), "+f"(d[1]), "+f"(d[2]), "+f"(d[3]), "+f"(d[4]), "+f"(d[5]), "+f"(d[6]), "+f"(d[7]),
        "+f"(d[8]), "+f"(d[9]), "+f"(d[10]), "+f"(d[11]), "+f"(d[12]), "+f"(d[13]), "+f"(d[14]), "+f"(d[15]),
        "+f"(d[16]), "+f"(d[17]), "+f"(d[18]), "+f"(d[19]), "+f"(d[20]), "+f"(d[21]), "+f"(d[22]), "+f"(d[23]),
        "+f"(d[24]), "+f"(d[25]), "+f"(d[26]), "+f"(d[27]), "+f"(d[28]), "+f"(d[29]), "+f"(d[30]), "+f"(d[31]),
        "+f"(d[32]), "+f"(d[33]), "+f"(d[34]), "+f"(d[35]), "+f"(d[36]), "+f"(d[37]), "+f"(d[38]), "+f"(d[39]),
        "+f"(d[40]), "+f"(d[41]), "+f"(d[42]), "+f"(d[43]), "+f"(d[44]), "+f"(d[45]), "+f"(d[46]), "+f"(d[47]),
        "+f"(d[48]), "+f"(d[49]), "+f"(d[50]), "+f"(d[51]), "+f"(d[52]), "+f"(d[53]), "+f"(d[54]), "+f"(d[55]),
        "+f"(d[56]), "+f"(d[57]), "+f"(d[58]), "+f"(d[59]), "+f"(d[60]), "+f"(d[61]), "+f"(d[62]), "+f"(d[63]),
        "+f"(d[64]), "+f"(d[65]), "+f"(d[66]), "+f"(d[67]), "+f"(d[68]), "+f"(d[69]), "+f"(d[70]), "+f"(d[71]),
        "+f"(d[72]), "+f"(d[73]), "+f"(d[74]), "+f"(d[75]), "+f"(d[76]), "+f"(d[77]), "+f"(d[78]), "+f"(d[79]),
        "+f"(d[80]), "+f"(d[81]), "+f"(d[82]), "+f"(d[83]), "+f"(d[84]), "+f"(d[85]), "+f"(d[86]), "+f"(d[87]),
        "+f"(d[88]), "+f"(d[89]), "+f"(d[90]), "+f"(d[91]), "+f"(d[92]), "+f"(d[93]), "+f"(d[94]), "+f"(d[95])
      : "r"(da), "n"(HA), "r"(db), "n"(HB), "r"(sc));
  }
};

struct FftConst {
  uint32_t f[2][4], fi[4][4];
  float ta[4], tb[4];
};
__device__ __forceinline__ void cis(int m, float scale, float& c, float& s) {
  const float a = (float)m * (-6.283185307179586f * scale);
  c = __cosf(a);
  s = __sinf(a);
}
__device__ __forceinline__ void fft_tables(uint32_t (&v)[12], int tw) {
  const int row = tw >> 2, ch = tw & 3;
#pragma unroll
  for (int i = 0; i < 4; i++) {
    float c[2], s[2], x[2];
#pragma unroll
    for (int e = 0; e < 2; e++) {
      cis((((32 * (8 * ch + 2 * i + e) + 15) * (4 * row - 63) + 2048) & 4095) - 2048, 1.f / 4096, c[e], s[e]);
      float gc, gs;
      cis((((row & 15) * (8 * (ch & 1) + 2 * i + e) + 8) & 15) - 8, 1.f / 16, gc, gs);
      x[e] = (row >> 4) == (ch >> 1) ? gc : (ch >> 1) ? gs : -gs;
    }
    v[i] = pack2(c[0] * 0.125f, c[1] * 0.125f);
    v[4 + i] = pack2(s[0] * 0.125f, s[1] * 0.125f);
    v[8 + i] = pack2(x[0], x[1]);
  }
#pragma unroll
  for (int i = 0; i < 12; i++) asm volatile("" : "+r"(v[i]));
}
__device__ __forceinline__ void fft_tables_store(const uint32_t (&v)[12], uint32_t sb, int tw) {
  const int row = tw >> 2;
  const uint32_t x = ((tw ^ (row >> 1)) & 3) << 4, a = sb + OFF_FT + (16 * (row >> 3) + (row & 7)) * 64 + x;
  sts128(a, v[0], v[1], v[2], v[3]);
  sts128(a + 512, v[4], v[5], v[6], v[7]);
  sts128(sb + OFF_GT + row * 64 + x, v[8], v[9], v[10], v[11]);
}
__device__ __forceinline__ void fft_twiddles(float (&v)[4], int tw) {
#pragma unroll
  for (int i = 0; i < 2; i++) {
    float c, s;
    cis((2 * (2 * (tw & 3) + i) - 15) * (4 * (tw >> 2) - 63), 1.f / 4096, c, s);
    v[2 * i] = __fdividef(-s, 1.f + c);
    v[2 * i + 1] = s;
  }
  pin<4>(v);
}
__device__ __forceinline__ void fft_matrices(FftConst& k, uint32_t sb, int w, int lane) {
  const uint32_t x = (lane >> 1) & 3;
  const uint4 t0 = lds128(sb + OFF_TT + 512 * w + 16 * lane), t1 = lds128(sb + OFF_TT + 512 * w + 16 * (lane ^ 3));
  k.ta[0] = __uint_as_float(t0.x); k.tb[0] = __uint_as_float(t0.y); k.ta[1] = __uint_as_float(t0.z); k.tb[1] = __uint_as_float(t0.w);
  k.ta[3] = __uint_as_float(t1.x); k.tb[3] = __uint_as_float(t1.y); k.ta[2] = __uint_as_float(t1.z); k.tb[2] = __uint_as_float(t1.w);
#pragma unroll
  for (int i = 0; i < 2; i++) {
    ldsm4(k.f[i], sb + OFF_FT + (16 * w + (lane & 15)) * 64 + (((2 * i + (lane >> 4)) ^ x) << 4));
    ldsm4t(k.fi[i], sb + OFF_FT + (32 * i + lane) * 64 + ((w ^ x) << 4));
#pragma unroll
    for (int j = 0; j < 4; j++) {
      k.fi[2 + i][j] = (j & 1) ? k.fi[i][j - 1] ^ 0x80008000u : k.fi[i][j + 1];
      asm volatile("" : "+r"(k.fi[2 + i][j]));
    }
  }
}
__device__ __forceinline__ void rot(bool inv, float& x, float& y, float a, float b) {
  x = fmaf(inv ? -a : a, y, x);
  y = fmaf(inv ? -b : b, x, y);
  x = fmaf(inv ? -a : a, y, x);
}
__device__ __forceinline__ void twiddle_fwd(uint32_t (&a)[4][4], float* d, const FftConst& k) {
#pragma unroll
  for (int q = 0; q < 4; q++)
#pragma unroll
    for (int j = 0; j < 2; j++) {
      float* x = d + 8 * q + 4 * j;
      rot(j, x[0], x[2], k.ta[2 * j], k.tb[2 * j]);
      rot(j, x[1], x[3], k.ta[2 * j + 1], k.tb[2 * j + 1]);
      a[q & 2][2 * j + (q & 1)] = pack2(x[0], x[1]);
      a[(q & 2) + 1][2 * j + (q & 1)] = pack2(x[2], x[3]);
    }
}
__device__ __forceinline__ void g_step(float* d, const uint32_t (&a)[4][4], uint32_t dre, uint32_t dim) {
  WgRS<32>::set<HI_SW64>(d, a[0], dre);
  WgRS<32>::set<HI_SW64>(d + 16, a[2], dre);
  WgRS<32>::mma<HI_SW64>(d, a[1], dim);
  WgRS<32>::mma<HI_SW64>(d + 16, a[3], dim);
  wg_commit();
}

__device__ __forceinline__ void conv_channel(const FftConst& k, uint32_t sb, int c, int wg, int w, int lane) {
  const uint32_t cb = sb + off_ch(c), bars = sb + OFF_BAR;
  const uint32_t du = desc_lo(cb, 1024), dg = desc_lo(sb + OFF_GT, 16), dz = desc_lo(cb + U_BYTES, 16);
  float U[32], H[32];
  uint32_t a[4][4], e[4][4];
  const float dv = __uint_as_float(lds32(sb + OFF_D + 4 * c));
  wg_fence();
  WgRS<64>::set<HI_SW32>(H, k.f[0], du + 256);
  WgRS<64>::mma<HI_SW32>(H, k.f[1], du + 256 + 32);
  wg_commit();
  wg_wait<0>();
  pin<32>(H);
  twiddle_fwd(a, H, k);
  if (ATT_GATE && H_EARLY) mbar_wait(bars + 8 * B_ATTN, 0);
  mbar_wait(bars + 8 * (B_U + (c < 3 ? c : 3)), 0);
  TSM(w == 0 && c < 3, 7 + wg);
  wg_fence();
  WgRS<64>::set<HI_SW32>(U, k.f[0], du);
  WgRS<64>::mma<HI_SW32>(U, k.f[1], du + 32);
  wg_commit();
  g_step(H, a, dg, dg + 64);
  wg_wait<1>();
  pin<32>(U);
  twiddle_fwd(e, U, k);
  wg_fence();
  g_step(U, e, dg, dg + 64);
  wg_wait<0>();
  pin<32>(U);
  pin<32>(H);
#pragma unroll
  for (int j = 0; j < 2; j++) {
    float pr[4][2], pi[4][2];
#pragma unroll
    for (int x = 0; x < 2; x++) {
      H[4 * j + x] += dv;
#pragma unroll
      for (int m = 0; m < 4; m++) {
#pragma unroll
        for (int q = 0; q <= m; q++) {
          const int ih = 16 * (q >> 1) + 2 * (q & 1) + 4 * j + x, iu = 16 * ((m - q) >> 1) + 2 * ((m - q) & 1) + 4 * j + x;
          pr[m][x] = q ? fmaf(H[ih], U[iu], pr[m][x]) : H[ih] * U[iu];
          pi[m][x] = q ? fmaf(H[ih], U[iu + 8], pi[m][x]) : H[ih] * U[iu + 8];
          pr[m][x] = fmaf(-H[ih + 8], U[iu + 8], pr[m][x]);
          pi[m][x] = fmaf(H[ih + 8], U[iu], pi[m][x]);
        }
      }
    }
#pragma unroll
    for (int m = 0; m < 4; m++) {
      a[m & 2][2 * j + (m & 1)] = pack2(pr[m][0], pr[m][1]);
      a[(m & 2) + 1][2 * j + (m & 1)] = pack2(pi[m][0], pi[m][1]);
    }
  }
  wg_fence();
  g_step(U, a, dg + 64, dg);
  const uint32_t za = cb + U_BYTES + (8 * w + (lane & 7)) * 128 + (((lane >> 3) ^ (lane & 7)) << 4);
  const uint32_t ya = cb + (lane >> 4) * 1024 + (8 * w + (lane & 7)) * 32 + ((((lane >> 3) ^ (lane >> 2)) & 1) << 4);
  wg_sync(1 + wg);
  wg_wait<0>();
  pin<32>(U);
  TSIF(w == 0, 80 + c);
#pragma unroll
  for (int p = 0; p < 2; p++) {
#pragma unroll
    for (int i = 0; i < 4; i++) {
      const int j = i & 1;
      float* x = U + 16 * p + 4 * j + (i & 2);
      rot(!j, x[8], x[0], k.ta[2 * j], k.tb[2 * j]);
      rot(!j, x[9], x[1], k.ta[2 * j + 1], k.tb[2 * j + 1]);
      e[p][i] = pack2(x[8], x[9]);
      e[2 + p][i] = pack2(x[0], x[1]);
    }
    stsm4(za ^ (64 * p), e[p]);
    stsm4((za ^ (64 * p)) + 4096, e[2 + p]);
  }
  fence_async_smem();
  wg_sync(1 + wg);
  wg_fence();
  WgRS<64>::set<HI_SW128>(H, k.fi[0], dz);
#pragma unroll
  for (int ks = 1; ks < 4; ks++) WgRS<64>::mma<HI_SW128>(H, k.fi[ks], dz + 128 * ks);
  wg_commit();
  wg_wait<0>();
  pin<32>(H);
  TSIF(w == 0, 88 + c);
#pragma unroll
  for (int j = 0; j < 8; j++)
    a[j >> 2][j & 3] = j < 2 ? pack2(H[4 * j], H[4 * j + 1]) : pack2(H[4 * j] + H[4 * j - 6], H[4 * j + 1] + H[4 * j - 5]);
  stsm4(ya, a[0]);
  stsm4(ya + 2048, a[1]);
  fence_async_smem();
  __syncwarp();
}

__device__ __forceinline__ void prep_slab(uint4* res, const uint2* sw, uint32_t sb, int slab, int w, int lane) {
  const int t = lane & 3, tp = (lane & 7) >> 1, pos = 8 * tp + 2 * (((lane >> 3) + tp) & 3) + (lane & 1);
  const uint32_t base = sb + OFF_KVS + slab * KVS_BYTES + pos * 128;
  uint32_t kk[2][4][4], vv[2][4];
  mbar_wait(sb + OFF_BAR + 8 * (B_KV + slab), 0);
#pragma unroll
  for (int h = 0; h < 2; h++) {
#pragma unroll
    for (int j = 0; j < 4; j++) {
      const uint32_t a = base + 128 * j;
      ldsm4t(kk[h][j], a + (((w + 4 * h) ^ ((a >> 7) & 7)) << 4));
    }
    const uint32_t a = base + KVS_V;
    ldsm4t(vv[h], a + (((w + 4 * h) ^ ((a >> 7) & 7)) << 4));
  }
#pragma unroll
  for (int h = 0; h < 2; h++) {
    uint32_t (&k)[4][4] = kk[h];
    uint32_t (&v)[4] = vv[h];
    const uint32_t w0 = __byte_perm(sw[h].x, 0, 0x1010), w1 = __byte_perm(sw[h].x, 0, 0x3232);
    const uint32_t w2 = __byte_perm(sw[h].y, 0, 0x1010), w3 = __byte_perm(sw[h].y, 0, 0x3232);
#pragma unroll
    for (int m = 0; m < 4; m++)
      v[m] = bmul(badd(badd(badd(bmul(k[0][m], w3), bmul(k[1][m], w2)), bmul(k[2][m], w1)), bmul(k[3][m], w0)), v[m]);
    uint32_t a[4];
#pragma unroll
    for (int m = 0; m < 4; m++) a[m] = (t & 1) ? v[(m + 3) & 3] : v[m];
    res[h] = (t & 2) ? make_uint4(a[2], a[3], a[0], a[1]) : make_uint4(a[0], a[1], a[2], a[3]);
  }
}

__device__ __forceinline__ void prep_gate(const Params& p, int b, int w, int lane) {
  uint2 gw[5], x[4][5];
#pragma unroll
  for (int j = 0; j < 5; j++) gw[j] = ldg64(reinterpret_cast<const uint2*>(p.gate_w) + lane + 32 * j);
#pragma unroll
  for (int i = 0; i < 4; i++)
#pragma unroll
    for (int j = 0; j < 5; j++)
      x[i][j] = ldg64(reinterpret_cast<const uint2*>(p.q) + (16 * b + 4 * w + i) * (DIM / 4) + lane + 32 * j);
  float s[4];
#pragma unroll
  for (int i = 0; i < 4; i++) {
    s[i] = 0.f;
#pragma unroll
    for (int j = 0; j < 5; j++) {
      const uint32_t m0 = bmul(x[i][j].x, gw[j].x), m1 = bmul(x[i][j].y, gw[j].y);
      s[i] += (bf_lo(m0) + bf_hi(m0)) + (bf_lo(m1) + bf_hi(m1));
    }
  }
  const bool h = lane & 16, q = lane & 8;
  const float a = (h ? s[2] : s[0]) + __shfl_xor_sync(0xffffffffu, h ? s[0] : s[2], 16);
  const float c = (h ? s[3] : s[1]) + __shfl_xor_sync(0xffffffffu, h ? s[1] : s[3], 16);
  float z = (q ? c : a) + __shfl_xor_sync(0xffffffffu, q ? a : c, 8);
#pragma unroll
  for (int o = 4; o > 0; o >>= 1) z += __shfl_xor_sync(0xffffffffu, z, o);
  z = bf_lo(pack2(z, 0.f));
  if ((lane & 7) == 0) g_gate[16 * b + 4 * w + (lane >> 3)] = bf_lo(pack2(__fdividef(1.f, 1.f + __expf(-z)), 0.f));
}

__device__ __forceinline__ uint32_t bmax(uint32_t a, uint32_t b) {
  uint32_t d;
  asm("max.bf16x2 %0, %1, %2;" : "=r"(d) : "r"(a), "r"(b));
  return d;
}
__device__ __forceinline__ void softmax_two(const float (&l)[2][2], uint32_t& p0, uint32_t& p1) {
  constexpr float kScale = 0.22360679774997896f, kLog2e = 1.4426950408889634f;
  const uint32_t r0 = pack2(l[0][0], l[1][0]), r1 = pack2(l[0][1], l[1][1]);
  const uint32_t x0 = pack2(bf_lo(r0) * kScale, bf_hi(r0) * kScale), x1 = pack2(bf_lo(r1) * kScale, bf_hi(r1) * kScale);
  uint32_t m = bmax(x0, x1);
  m = bmax(m, __shfl_xor_sync(0xffffffffu, m, 1));
  m = bmax(m, __shfl_xor_sync(0xffffffffu, m, 2));
  const float m0 = bf_lo(m) * kLog2e, m1 = bf_hi(m) * kLog2e;
  p0 = pack2(ex2(bf_lo(x0) * kLog2e - m0), ex2(bf_lo(x1) * kLog2e - m0));
  p1 = pack2(ex2(bf_hi(x0) * kLog2e - m1), ex2(bf_hi(x1) * kLog2e - m1));
}

__device__ __forceinline__ void halo_read(uint32_t (&kpv)[10], uint32_t (&vpv)[10], uint32_t (&tg)[7], const uint4* hp) {
#pragma unroll
  for (int j = 0; j < 7; j++) {
    uint32_t x0, x1, x2;
    asm volatile("ld.relaxed.gpu.global.v4.u32 {%0, %1, %2, %3}, [%4];"
                 : "=r"(x0), "=r"(x1), "=r"(x2), "=r"(tg[j]) : "l"(hp + 32 * j) : "memory");
    if (j < 4) kpv[3 * j] = x0; else vpv[3 * j - 10] = x0;
    if (j < 3) kpv[3 * j + 1] = x1; else vpv[3 * j - 9] = x1;
    if (j < 3) kpv[3 * j + 2] = x2; else if (j < 6) vpv[3 * j - 8] = x2;
  }
}

template <int ROT>
__device__ __forceinline__ void pack_qkv(const float* acc, uint32_t (&qlo)[10], uint32_t (&qhi)[10], uint32_t (&klo)[10],
                                         uint32_t (&khi)[10], uint32_t (&vlo)[10], uint32_t (&vhi)[10]) {
#pragma unroll
  for (int j = 0; j < 10; j++) {
    const int x = (j + ROT) % 10, tq = x < 8 ? x : 16 + x, tk = x < 8 ? 8 + x : 18 + x, tv = x < 8 ? 16 + x : 20 + x;
    khi[j] = pack2(acc[4 * tk + 2], acc[4 * tk + 3]);
    vhi[j] = movm(pack2(acc[4 * tv + 2], acc[4 * tv + 3]));
    qlo[j] = pack2(acc[4 * tq], acc[4 * tq + 1]);
    qhi[j] = pack2(acc[4 * tq + 2], acc[4 * tq + 3]);
    klo[j] = pack2(acc[4 * tk], acc[4 * tk + 1]);
    vlo[j] = pack2(acc[4 * tv], acc[4 * tv + 1]);
    asm volatile("" : "+r"(khi[j]), "+r"(qlo[j]), "+r"(qhi[j]), "+r"(klo[j]), "+r"(vlo[j]));
  }
}

template <int ROT> __device__ __forceinline__ void halo_send(const float* acc, uint4* ho, uint32_t tag) {
#pragma unroll
  for (int j = 0; j < 7; j++) {
    uint32_t x[3];
#pragma unroll
    for (int e = 0; e < 3; e++) {
      const int i = 3 * j + e, y = (i % 10 + ROT) % 10, tk = y < 8 ? 8 + y : 18 + y, tv = y < 8 ? 16 + y : 20 + y;
      x[e] = i < 10 ? pack2(acc[4 * tk + 2], acc[4 * tk + 3]) : i < 20 ? movm(pack2(acc[4 * tv + 2], acc[4 * tv + 3])) : 0u;
    }
    asm volatile("st.relaxed.gpu.global.v4.u32 [%0], {%1, %2, %3, %4};" ::"l"(ho + 32 * j), "r"(x[0]), "r"(x[1]), "r"(x[2]), "r"(tag) : "memory");
  }
}

__device__ __forceinline__ void attention(float* acc, uint32_t sb, int b, int par, int w, int lane, uint32_t tag) {
  const int g = lane >> 2, t = lane & 3;
  uint32_t klo[10], khi[10], vlo[10], vhi[10], qlo[10], qhi[10], kpv[10], vpv[10];
  if (HALO_FIRST && w == 3 && b < NCTA - 8) {
    uint4* ho = g_halo + (b * 2 + par) * 224 + lane;
    if (tail_first(b & 7)) halo_send<8>(acc, ho, tag);
    else halo_send<0>(acc, ho, tag);
    TSIF(par == 0, 76);
    pin<120>(acc);
  }
  if (tail_first(b & 7)) pack_qkv<8>(acc, qlo, qhi, klo, khi, vlo, vhi);
  else pack_qkv<0>(acc, qlo, qhi, klo, khi, vlo, vhi);
  const uint32_t xa = sb + OFF_KVX + (par * 3) * 2560 + lane * 16;
  if (w < 3) {
    sts128(xa + w * 2560, khi[0], khi[1], khi[2], khi[3]);
    sts128(xa + w * 2560 + 512, khi[4], khi[5], khi[6], khi[7]);
    sts128(xa + w * 2560 + 1024, khi[8], khi[9], vhi[0], vhi[1]);
    sts128(xa + w * 2560 + 1536, vhi[2], vhi[3], vhi[4], vhi[5]);
    sts128(xa + w * 2560 + 2048, vhi[6], vhi[7], vhi[8], vhi[9]);
  } else if (!HALO_FIRST && b < NCTA - 8) {
    uint4* ho = g_halo + (b * 2 + par) * 224 + lane;
#pragma unroll
    for (int j = 0; j < 7; j++) {
      const uint32_t x0 = j < 4 ? khi[3 * j] : vhi[3 * j - 10], x1 = j < 3 ? khi[3 * j + 1] : vhi[3 * j - 9];
      const uint32_t x2 = j < 3 ? khi[3 * j + 2] : j < 6 ? vhi[3 * j - 8] : 0u;
      asm volatile("st.relaxed.gpu.global.v4.u32 [%0], {%1, %2, %3, %4};" ::"l"(ho + 32 * j), "r"(x0), "r"(x1), "r"(x2), "r"(tag) : "memory");
    }
  }
  TSIF(par == 0 && w == 1, 64);
  TSIF(par == 0 && w == 3 && !HALO_FIRST, 76);
#pragma unroll
  for (int j = 0; j < 10; j++) vlo[j] = movm(vlo[j]);
  const bool far0 = 2 * t > g, far1 = 2 * t + 1 > g;
  const uint32_t mfar = (far0 ? 0x0000FFFFu : 0u) | (far1 ? 0xFFFF0000u : 0u);
  float slo[4][2], shi[4][2], lg[2][2];
  uint32_t phi[4], plo[4], qml[4], qmh[4];
#pragma unroll
  for (int h = 0; h < 4; h++) {
    const int f = h == 0 ? 0 : h == 1 ? 3 : h == 2 ? 5 : 8, hf = h < 2 ? 2 : 7;
    const bool mine = (h & 1) ? t >= 2 : t < 2;
    qml[h] = mine ? qlo[hf] : 0u;
    qmh[h] = mine ? qhi[hf] : 0u;
    float a[4] = {0.f, 0.f, 0.f, 0.f}, c[4] = {0.f, 0.f, 0.f, 0.f};
    mma16816(a, qlo[f], qhi[f], qlo[f + 1], qhi[f + 1], klo[f], klo[f + 1]);
    mma16816(c, qlo[f], qhi[f], qlo[f + 1], qhi[f + 1], khi[f], khi[f + 1]);
    mma1688(a, qml[h], qmh[h], klo[hf]);
    mma1688(c, qml[h], qmh[h], khi[hf]);
    slo[h][0] = a[0];
    slo[h][1] = a[1];
    shi[h][0] = lg[h & 1][0] = far0 ? a[2] : c[2];
    shi[h][1] = lg[h & 1][1] = far1 ? a[3] : c[3];
    if (!ATT_MERGE && (h & 1)) softmax_two(lg, phi[h - 1], phi[h]);
  }
  TSIF(par == 0 && w == 1, 65);
  wg_sync(1 + par);
  TSIF(par == 0 && w == 1, 66);
  const bool nohist = (w == 0) && (b < 8);
  const uint4* hp = g_halo + ((b - 8) * 2 + par) * 224 + lane;
  uint32_t tg[7];
  if (w > 0) {
    const uint4 v0 = lds128(xa + (w - 1) * 2560), v1 = lds128(xa + (w - 1) * 2560 + 512), v2 = lds128(xa + (w - 1) * 2560 + 1024);
    const uint4 v3 = lds128(xa + (w - 1) * 2560 + 1536), v4 = lds128(xa + (w - 1) * 2560 + 2048);
    kpv[0] = v0.x; kpv[1] = v0.y; kpv[2] = v0.z; kpv[3] = v0.w; kpv[4] = v1.x; kpv[5] = v1.y; kpv[6] = v1.z; kpv[7] = v1.w;
    kpv[8] = v2.x; kpv[9] = v2.y; vpv[0] = v2.z; vpv[1] = v2.w; vpv[2] = v3.x; vpv[3] = v3.y; vpv[4] = v3.z; vpv[5] = v3.w;
    vpv[6] = v4.x; vpv[7] = v4.y; vpv[8] = v4.z; vpv[9] = v4.w;
  } else if (nohist) {
#pragma unroll
    for (int j = 0; j < 10; j++) kpv[j] = vpv[j] = 0u;
  } else {
    TSIF(par == 0, 77);
    halo_read(kpv, vpv, tg, hp);
  }
  if (w == 0 && !nohist) {
    int spins = 0;
    while (true) {
      bool ok = true;
#pragma unroll
      for (int j = 0; j < 7; j++) ok = ok && tg[j] == tag;
      if (__all_sync(0xffffffffu, ok) || ++spins > SPIN_LIMIT) break;
      halo_read(kpv, vpv, tg, hp);
    }
    TSIF(par == 0, 79);
  }
#pragma unroll
  for (int h = 0; h < 4; h++) {
    const int f = h == 0 ? 0 : h == 1 ? 3 : h == 2 ? 5 : 8, hf = h < 2 ? 2 : 7;
    float a[4] = {0.f, 0.f, 0.f, 0.f};
    mma16816(a, qlo[f], qhi[f], qlo[f + 1], qhi[f + 1], kpv[f], kpv[f + 1]);
    mma1688(a, qml[h], qmh[h], kpv[hf]);
    const float ninf = __int_as_float(0xff800000);
    lg[h & 1][0] = far0 ? (nohist ? ninf : a[0]) : slo[h][0];
    lg[h & 1][1] = far1 ? (nohist ? ninf : a[1]) : slo[h][1];
    if (h & 1) {
      softmax_two(lg, plo[h - 1], plo[h]);
      if (ATT_MERGE) {
        const float lh[2][2] = {{shi[h - 1][0], shi[h - 1][1]}, {shi[h][0], shi[h][1]}};
        softmax_two(lh, phi[h - 1], phi[h]);
      }
    }
  }
  TSIF(par == 0 && w <= 1, 67 + w);
  uint32_t ov[20];
#pragma unroll
  for (int hp = 0; hp < 2; hp++) {
    const int hf = hp ? 7 : 2;
    float sh[4] = {0.f, 0.f, 0.f, 0.f}, i0 = 0.f, i1 = 0.f;
#pragma unroll
    for (int e = 0; e < 2; e++) {
      const int h = 2 * hp + e, f = h == 0 ? 0 : h == 1 ? 3 : h == 2 ? 5 : 8;
      const uint32_t a0 = plo[h] & mfar, a2 = plo[h] & ~mfar, a3 = phi[h] & mfar, c1 = phi[h] & ~mfar;
      float sum[4] = {0.f, 0.f, 0.f, 0.f};
      mma1688(sum, plo[h], phi[h], 0x3F803F80u);
      const float r0 = rcp(sum[0]), r1 = rcp(sum[2]);
#pragma unroll
      for (int j = f; j < f + 2; j++) {
        float o[4] = {0.f, 0.f, 0.f, 0.f};
        mma16816(o, a0, 0u, a2, a3, vpv[j], vlo[j]);
        mma1688(o, 0u, c1, vhi[j]);
        ov[2 * j] = pack2(o[0] * r0, o[1] * r0);
        ov[2 * j + 1] = pack2(o[2] * r1, o[3] * r1);
      }
      const bool mine = e ? g >= 4 : g < 4;
      mma16816(sh, a0, 0u, a2, a3, mine ? vpv[hf] : 0u, mine ? vlo[hf] : 0u);
      mma1688(sh, 0u, c1, mine ? vhi[hf] : 0u);
      if (e == 0 || t >= 2) {
        i0 = r0;
        i1 = r1;
      }
    }
    ov[2 * hf] = pack2(sh[0] * i0, sh[1] * i0);
    ov[2 * hf + 1] = pack2(sh[2] * i1, sh[3] * i1);
  }
  TS(32 + 4 * par + w);
  mbar_wait(sb + OFF_BAR + 8 * B_P1, 0);
  const uint32_t oa = sb + OFF_OA + (lane >> 4) * 2048 + (32 * w + 2 * (lane & 15) + par) * 16;
#pragma unroll
  for (int j = 0; j < 5; j++) stsm4(oa + 4096 * j, ov + 4 * j);
  TSIF(par == 0 && w == 0, 120);
  fence_async_smem();
  TSIF(par == 0 && w == 0, 121);
  __syncwarp();
  if (lane == 0) mbar_arrive(sb + OFF_BAR + 8 * B_ATTN);
  TSM(w == 0 || w == 2, 122 + par + (w == 2 ? 3 : 0));
}

struct Maps {
  CUtensorMap x, wm, wt, k, v, y, wo, qm, qt, om, ot, u;
};

__device__ __forceinline__ void load_stage(uint32_t sb, int kb, int b, const Maps& m) {
  const uint32_t st = sb + (kb & 3) * STAGE_BYTES, bar = sb + OFF_BAR + 8 * (B_FULL1 + (kb & 3));
  const int r = b >> 3, hg = b & 7, slab = kb - KV_KB;
  const bool kv = slab >= 0 && slab < 5;
  const uint32_t kbar = sb + OFF_BAR + 8 * (B_KV + slab), dst = sb + OFF_KVS + slab * KVS_BYTES;
  mbar_expect_tx(bar, STAGE_BYTES);
  if (kv) mbar_expect_tx(kbar, KVS_BYTES);
  tma_3d(st, &m.x, 64 * kb, 64 * r, 0, bar);
  if (kv && KV_MIX) tma_3d(dst, &m.k, 0, 32 * (b >> 1) - 3, 2 * slab + (b & 1), kbar);
  tma_3d(st + ST_W, &m.wm, 80 * hg + (tail_first(hg) ? 16 : 0), 64 * kb, 0, bar);
  if (kv && KV_MIX) tma_3d(dst + KVS_V, &m.v, 0, 32 * (b >> 1), 2 * slab + (b & 1), kbar);
  tma_3d(st + ST_WT, &m.wt, 80 * hg + (tail_first(hg) ? 0 : 64), 64 * kb, 0, bar);
  if (kv && !KV_MIX) tma_3d(dst, &m.k, 0, 32 * (b >> 1) - 3, 2 * slab + (b & 1), kbar);
  if (kv && !KV_MIX) tma_3d(dst + KVS_V, &m.v, 0, 32 * (b >> 1), 2 * slab + (b & 1), kbar);
}

__global__ void __launch_bounds__(NTHR, 1) fused_kernel(const __grid_constant__ Maps m, const Params p) {
  extern __shared__ __align__(1024) uint8_t smem[];
  const uint32_t sb = (uint32_t)__cvta_generic_to_shared(smem);
  const uint32_t bars = sb + OFF_BAR;
  const int tid = threadIdx.x, lane = tid & 31;
  int b = blockIdx.x;
  if (BMAP == 1) b = (((b & 63) >> 3) * 2 + (b & 1)) * 8 + (((b < 64 ? 0x6521 : 0x7430) >> (4 * ((b >> 1) & 3))) & 7);
  if (BMAP == 2) b = ((b & 63) >> 2) * 8 + (((b < 64 ? 0x6521 : 0x7430) >> (4 * (b & 3))) & 7);
  if (BMAP == 3) b = (((b & 63) >> 3) * 2 + (b & 1)) * 8 + (((b < 64 ? 0x7430 : 0x6521) >> (4 * ((b >> 1) & 3))) & 7);
  if (BMAP == 4) b = (((b >> 4) * 2 + (b & 1)) * 8) + ((b >> 1) & 7);
  if (BMAP == 5) b = 127 - b;
  const int r = b >> 3, hg = b & 7;

  if (tid == T_ISSUE) {
    TSM(true, 0);
#pragma unroll
    for (int i = 0; i < 4; i++) mbar_init(bars + 8 * (B_FULL1 + i), 1);
#pragma unroll
    for (int i = 0; i < 3; i++) mbar_init(bars + 8 * (B_KV + i), 1);
    fence_async_smem();
#pragma unroll 1
    for (int kb = 0; kb <= PRE2; kb++) load_stage(sb, kb, b, m);
  } else if (tid >= T_PF && tid < T_PF + 12) {
    tm_prefetch(&m.x + (tid - T_PF));
  } else if (tid == T_INIT) {
#pragma unroll
    for (int i = 0; i < 4; i++) mbar_init(bars + 8 * (B_EMPTY1 + i), 8);
#pragma unroll
    for (int i = 0; i < 8; i++) mbar_init(bars + 8 * (B_FULL2 + i), 1);
#pragma unroll
    for (int i = 0; i < 4; i++) mbar_init(bars + 8 * (B_EMPTY2 + i), 8);
#pragma unroll
    for (int i = 0; i < 4; i++) mbar_init(bars + 8 * (B_U + i), 1);
    mbar_init(bars + 8 * B_HA, 4);
    mbar_init(bars + 8 * B_GATE, 4);
    mbar_init(bars + 8 * B_HB, 1);
    mbar_init(bars + 8 * B_KVD, 4);
    mbar_init(bars + 8 * B_QF, 1);
    mbar_init(bars + 8 * B_ATTN, 8);
    mbar_init(bars + 8 * B_P1, 8);
    mbar_init(bars + 8 * B_C34, 1);
#pragma unroll
    for (int i = 0; i < 5; i++) mbar_init(bars + 8 * (B_YST + i), 4);
#pragma unroll
    for (int i = 0; i < 5; i++) mbar_init(bars + 8 * (B_US + i), 4);
    mbar_init(bars + 8 * B_YSIG, 1);
    mbar_init(bars + 8 * B_YFULL, 1);
    mbar_init(bars + 8 * B_EPOCH, 1);
    mbar_init(bars + 8 * B_PREP, 4);
    mbar_init(bars + 8 * B_USIG, 1);
    mbar_init(bars + 8 * B_WST, 1);
#pragma unroll
    for (int i = 3; i < 5; i++) mbar_init(bars + 8 * (B_KV + i), 1);
    mbar_init(bars + 8 * B_E3, 8);
    mbar_init(bars + 8 * B_LAST, 1);
    mbar_init(bars + 8 * B_OSIG, 1);
    mbar_init(bars + 8 * B_WOP, 1);
    fence_async_smem();
  }
  const int warp = __shfl_sync(0xffffffffu, tid >> 5, 0), wg = warp >> 2, w = warp & 3;
  __syncthreads();

  if (wg == 3) {
    asm volatile("setmaxnreg.dec.sync.aligned.u32 56;");
    if (w == 0) {
      if (lane == 0) {
#pragma unroll 1
        for (int kb = 1 + PRE2; kb < 10; kb++) {
          if (kb >= 4) mbar_wait(bars + 8 * (kb == 7 ? B_E3 : B_EMPTY1 + (kb & 3)), (kb >> 3) & 1);
          TSIF(kb >= 4, 44 + kb);
          load_stage(sb, kb, b, m);
          TSIF(kb == 3, 60);
          if (kb == TRIG_KB) mbar_arrive(bars + 8 * B_LAST);
        }
        mbar_wait(bars + 8 * B_WOP, 0);
        mbar_wait(bars + 8 * WL_TRIG, 0);
        mbar_wait(bars + 8 * B_EPOCH, 0);
        flag_wait(g_cnt + C_W + 32 * hg, (lds32(sb + OFF_EPOCH) + 1) * 16);
        TS(30);
#pragma unroll 1
        for (int j = 0; j < 8; j++) {
          if (j >= 6) mbar_wait(bars + 8 * (B_EMPTY2 + j - 6), 0);
          if (j == 4) mbar_wait(bars + 8 * B_ATTN, 0);
          TSIF(j >= 6, 100 + j);
          if (RF_GATE && j == 6) mbar_wait(bars + 8 * B_YSIG, 0);
          mbar_expect_tx(bars + 8 * (B_FULL2 + j), j == 0 ? WO_BYTES : j == 5 ? O_BYTES + WO_BYTES + 512 : O_BYTES + WO_BYTES);
          bulk_load(sb + off_w(j), g_WO + (hg * 8 + step_src(hg, j)) * 800, WO_BYTES, bars + 8 * (B_FULL2 + j));
        }
        mbar_wait(bars + 8 * (B_EMPTY2 + 3), 0);
        mbar_expect_tx(bars + 8 * B_QF, O_BYTES);
        tma_2d(sb + OFF_QS, &m.qm, 80 * hg, 128 * r, bars + 8 * B_QF);
        tma_2d(sb + OFF_QT, &m.qt, 80 * hg + 64, 128 * r, bars + 8 * B_QF);
      }
    } else if (w == 1) {
      unsigned epoch = 0;
      if (lane == 0) {
        epoch = atomicAdd(g_cnt + C_LAUNCH, 1u) / NCTA;
        asm volatile("st.shared.u32 [%0], %1;" ::"r"(sb + OFF_EPOCH), "r"(epoch) : "memory");
        mbar_arrive(bars + 8 * B_EPOCH);
        mbar_wait(bars + 8 * B_KVD, 0);
        mbar_expect_tx(bars + 8 * B_HB, 5 * 4096);
#pragma unroll 1
        for (int c = 0; c < 5; c++) {
          if (c == 3) mbar_wait(bars + 8 * B_S3, 0);
          bulk_load(sb + off_ch(c) + U_BYTES, p.ssm_k + (5 * b + c) * SEQ, 4096, bars + 8 * B_HB);
        }
#pragma unroll
        for (int c = 0; c < 4; c++) mbar_expect_tx(bars + 8 * (B_U + c), c < 3 ? U_BYTES : 2 * U_BYTES);
        const uint4* usrc = g_U + 5 * b * U_PITCH;
        mbar_wait(bars + 8 * B_USIG, 0);
        flag_wait(g_cnt + C_PREP + 32 * (b & 15), (epoch + 1) * NCTA);
        TS(23);
#pragma unroll
        for (int c = 0; c < 5; c++) {
          if (c == 3) mbar_wait(bars + 8 * (B_U + 2), 0);
          bulk_load(sb + off_ch(c), usrc + c * U_PITCH, U_BYTES, bars + 8 * (B_U + (c < 3 ? c : 3)));
          TSIF(c == 0 || c == 4, 116 + (c >> 2));
        }
      }
      epoch = __shfl_sync(0xffffffffu, epoch, 0);
      if (lane < 8) {
        const int src = (b & ~7) | step_src(hg, lane);
        mbar_wait(bars + 8 * B_OSIG, 0);
        TS(20);
        flag_wait(g_cnt + C_O + 32 * src, epoch + 1);
        if (lane >= 1 && lane < 4) bulk_load(sb + off_o(lane), g_O + src * 1280, O_BYTES, bars + 8 * (B_FULL2 + lane));
        __syncwarp(0xff);
        TS(21);
        if (lane == 5) bulk_load(sb + OFF_GATE, g_gate + 128 * r, 512, bars + 8 * (B_FULL2 + 5));
#pragma unroll 1
        for (int j = 4; j < 8; j++) {
          if (lane == j) {
            mbar_wait(bars + 8 * (j < 6 ? B_C34 : B_EMPTY2 + j - 6), 0);
            if (RF_GATE && j == 6) mbar_wait(bars + 8 * B_YSIG, 0);
            bulk_load(sb + off_o(j), g_O + src * 1280, O_BYTES, bars + 8 * (B_FULL2 + j));
          }
          __syncwarp(0xff);
        }
        TS(22);
      }
    } else if (w == 2) {
      mbar_wait(bars + 8 * B_PREP, 0);
      if (!(NOMB & 8)) flag_signal(g_cnt + C_PREP, 16, lane);
      else if (lane < 16) flag_bump(g_cnt + C_PREP + 32 * lane);
      TS(25);
      if (lane == 0) mbar_arrive(bars + 8 * B_USIG);
      mbar_wait(bars + 8 * B_GATE, 0);
      if ((NOMB & 1) && lane == 0) asm volatile("fence.release.gpu;" ::: "memory");
      mbar_wait(bars + 8 * B_ATTN, 0);
      if (lane == 0) {
        if (O_DEFER) mbar_wait(bars + 8 * (B_U + 3), 0);
        asm volatile("cp.async.bulk.global.shared::cta.bulk_group [%0], [%1], 20480;\ncp.async.bulk.commit_group;\n"
                     "cp.async.bulk.wait_group 0;\nfence.proxy.async.global;" ::"l"(g_O + b * 1280), "r"(sb + OFF_OA) : "memory");
      }
      TS(74);
      if (!(NOMB & 1)) flag_signal(g_cnt + C_O + 32 * b, 1, lane);
      else if (lane == 0) flag_bump(g_cnt + C_O + 32 * b);
      TS(26);
      if (lane == 0) mbar_arrive(bars + 8 * B_OSIG);

    } else {
      if (lane == 0) {
        uint4* dst = g_WO + (hg * 8 + (r >> 1)) * 800 + (r & 1) * 80;
        mbar_wait(bars + 8 * B_P1, 0);
        mbar_wait(bars + 8 * WB_TRIG, 0);
        mbar_expect_tx(bars + 8 * B_WST, WO_BYTES / 2);
        tma_3d(sb + OFF_WS, &m.wo, 0, 40 * r, 5 * hg, bars + 8 * B_WST);
        mbar_wait(bars + 8 * B_WST, 0);
        mbar_wait(bars + 8 * WO_TRIG, 0);
#pragma unroll 1
        for (int n = 0; n < 5; n++)
          asm volatile("cp.async.bulk.global.shared::cta.bulk_group [%0], [%1], 1280;" ::"l"(dst + 160 * n), "r"(sb + OFF_WS + 1280 * n) : "memory");
        asm volatile("cp.async.bulk.commit_group;\ncp.async.bulk.wait_group 0;\nfence.proxy.async.global;" ::: "memory");
        if (!(NOMB & 4)) asm volatile("fence.release.gpu;" ::: "memory");
        flag_bump(g_cnt + C_W + 32 * hg);
        mbar_arrive(bars + 8 * B_WOP);
        TS(71);
#pragma unroll 1
        for (int c = 0; c < 5; c++) {
          mbar_wait(bars + 8 * (B_YST + c), 0);
          asm volatile("cp.async.bulk.global.shared::cta.bulk_group [%0], [%1], 4096;\ncp.async.bulk.commit_group;"
                       ::"l"(g_Y + (5 * b + c) * Y_PITCH), "r"(sb + off_ch(c)) : "memory");
          if (c == 2) {
            asm volatile("cp.async.bulk.wait_group.read 0;" ::: "memory");
            mbar_arrive(bars + 8 * B_C34);
          }
        }
        asm volatile("cp.async.bulk.wait_group 0;\nfence.proxy.async.global;" ::: "memory");
        TS(75);
        if (!(NOMB & 2)) asm volatile("fence.release.gpu;" ::: "memory");
        flag_bump(g_cnt + C_Y + 32 * (b >> 4));
        TS(27);
        mbar_arrive(bars + 8 * B_YSIG);
        mbar_expect_tx(bars + 8 * B_YFULL, 20480);
        flag_wait(g_cnt + C_Y + 32 * hg, (lds32(sb + OFF_EPOCH) + 1) * 16);
        TS(24);
        tma_2d(sb + OFF_YT, &m.y, 128 * r, 80 * hg, bars + 8 * B_YFULL);
        tma_2d(sb + OFF_YT + 10240, &m.y, 128 * r + 64, 80 * hg, bars + 8 * B_YFULL);
      }
    }
  } else {
    asm volatile("setmaxnreg.inc.sync.aligned.u32 152;");
    if (wg < 2) {
      float acc[120];
#pragma unroll
      for (int i = 0; i < 120; i++) acc[i] = 0.f;
      const uint32_t da = desc_lo(sb + wg * 8192, 16), db = desc_lo(sb + ST_W, 8192), dc = desc_lo(sb + ST_WT, 2048);
      if (PW1) pin<120>(acc);
      if (PW1 == 2) mbar_wait(bars + 8 * B_FULL1, 0);
#pragma unroll 1
      for (int kb = 0; kb < 10; kb++) {
        mbar_wait(bars + 8 * (B_FULL1 + (kb & 3)), (kb >> 2) & 1);
        const uint32_t so = (kb & 3) * (STAGE_BYTES >> 4);
        wg_fence();
#pragma unroll
        for (int k = 0; k < 4; k++) {
          WgSST<192>::mma<HI_SW128, HI_SW128>(acc, da + so + 2 * k, db + so + 128 * k, 1);
          WgSST<48>::mma<HI_SW128, HI_SW32>(acc + 96, da + so + 2 * k, dc + so + 32 * k, 1);
        }
        wg_commit();
        wg_wait<1>();
        if (kb > 0 && lane == 0) mbar_arrive(bars + 8 * (kb == 4 ? B_E3 : B_EMPTY1 + ((kb - 1) & 3)));
      }
      mbar_wait(bars + 8 * B_EPOCH, 0);
      const uint32_t tag = lds32(sb + OFF_EPOCH) + 1;
      mbar_wait(bars + 8 * B_S3, 0);
      wg_wait<0>();
      pin<120>(acc);
      if (lane == 0) mbar_arrive(bars + 8 * B_P1);
      TSM(w == 0, 3 + wg);
      attention(acc, sb, b, wg, w, lane, tag);
    } else {
      const int tw = tid & 127, chl = 64 * (b & 1) + 8 * w + (lane >> 2);
      uint4* up = g_U + chl * U_PITCH + ((4 * (b >> 1) + (lane & 3)) ^ ((b >> 2) & 1));
      uint2 sw[10];
      uint32_t dv = 0;
      if (lane < 5) dv = __ldg(reinterpret_cast<const unsigned short*>(p.ssm_D) + 5 * b + lane);
#pragma unroll
      for (int i = 0; i < 10; i++) sw[i] = ldg64(reinterpret_cast<const uint2*>(p.shift_k) + chl + 128 * (i >> 1) + 32 * (i & 1));
      uint32_t tab[12];
      float tt[4];
      fft_tables(tab, tw);
      fft_twiddles(tt, tw);
      uint4 res[10];
#pragma unroll
      for (int i = 0; i < 10; i++) res[i] = make_uint4(0, 0, 0, 0);
#pragma unroll 1
      for (int slab = 0; slab < 5; slab++) {
#pragma unroll
        for (int i = 0; i < 8; i++) res[i] = res[i + 2];
        prep_slab(res + 8, sw, sb, slab, w, lane);
        TSIF(w == 0, 99 + 4 * slab);
#pragma unroll
        for (int i = 0; i < 8; i++) sw[i] = sw[i + 2];
      }
      TSIF(w == 0, 28);
      __syncwarp();
      if (lane == 0) mbar_arrive(bars + 8 * B_KVD + ((res[8].x ^ res[9].x) & p.zero));
      mbar_wait(bars + 8 * B_KVD, 0);
      fft_tables_store(tab, sb, tw);
      mbar_wait(bars + 8 * B_LAST, 0);
#pragma unroll
      for (int i = 0; i < 10; i++) up[(128 * (i >> 1) + 32 * (i & 1)) * U_PITCH] = res[i];
      __syncwarp();
      if (lane == 0) mbar_arrive(bars + 8 * B_PREP);
      TSIF(w == 0 && !U_TMA, 5);
      mbar_wait(bars + 8 * (G_AFTER ? B_USIG : B_LAST), 0);
      if (!(SKIP & 1)) prep_gate(p, b, w, lane);
      __syncwarp();
      if (lane == 0) mbar_arrive(bars + 8 * B_GATE);
      TSIF(w == 0, 72);
      mbar_wait(bars + 8 * B_HB, 0);
      TSIF(w == 0, 2);
      const uint32_t ha = sb + U_BYTES + ((tw >> 3) * 16 + 8 + (tw & 7)) * 16;
      uint4 hv[5];
#pragma unroll
      for (int c = 0; c < 5; c++) hv[c] = lds128(ha + off_ch(c));
      __syncwarp();
#pragma unroll
      for (int c = 0; c < 5; c++) sts128((ha ^ 16) + off_ch(c), hv[c].x, hv[c].y, hv[c].z, hv[c].w);
      sts128(sb + OFF_TT + 16 * tw, __float_as_uint(tt[0]), __float_as_uint(tt[1]), __float_as_uint(tt[2]), __float_as_uint(tt[3]));
      if (tw < 5) asm volatile("st.shared.f32 [%0], %1;" ::"r"(sb + OFF_D + 4 * tw), "f"(bf_lo(dv) * 0.125f) : "memory");
      fence_async_smem();
      __syncwarp();
      if (lane == 0) mbar_arrive(bars + 8 * B_HA);
      TSIF(w == 0, 6);
    }

    FftConst fc;
    TSM(w == 0 && wg == 0, 104);
    mbar_wait(bars + 8 * B_HA, 0);
    fft_matrices(fc, sb, w, lane);
    TSM(w == 0 && wg == 0, 105);
    if (ATT_GATE && !H_EARLY) mbar_wait(bars + 8 * B_ATTN, 0);
    TSM(w == 0 && wg == 2, 124);
#pragma unroll 1
    for (uint32_t tasks = wg == 0 ? TASK0 : wg == 1 ? TASK1 : TASK2; tasks; tasks >>= 4) {
      const int c = (tasks & 7) - 1;
      conv_channel(fc, sb, c, wg, w, lane);
      if (lane == 0) mbar_arrive(bars + 8 * (B_YST + c));
      TSM(w == 0, 10 + c);
    }

    if (wg < 2) {
      const int g = lane >> 2;
      float acc[40];
#pragma unroll
      for (int i = 0; i < 40; i++) acc[i] = 0.f;
      const uint32_t da = desc_lo(sb + wg * 1024, 2048), db = desc_lo(sb, 2560);
      mbar_wait(bars + 8 * B_ATTN, 0);
      mbar_wait(bars + 8 * (B_YST + 3), 0);
      mbar_wait(bars + 8 * (B_YST + 4), 0);
      if (PW2) mbar_wait(bars + 8 * B_FULL2, 0);
      TSM(w == 0, 15 + wg);
#pragma unroll 1
      for (int j = 0; j < 8; j++) {
        mbar_wait(bars + 8 * (B_FULL2 + j), 0);
        const uint32_t oa = da + (off_o(j) >> 4), ob = db + (off_w(j) >> 4);
        wg_fence();
#pragma unroll
        for (int k = 0; k < 5; k++) WgSST<80>::mma<HI_NONE, HI_SW32>(acc, oa + 256 * k, ob + 32 * k, 1);
        wg_commit();
        wg_wait<1>();
        if (j >= 1 && j <= 4 && lane == 0) mbar_arrive(bars + 8 * (B_EMPTY2 + j - 1));
      }
      TSIF(w == 0 && wg == 0, 113);
      const int tr = 64 * wg + 16 * w + (lane & 15);
      const uint32_t fm = sb + OFF_QS + tr * 128, fx = (lane >> 4) ^ (tr & 7);
      const uint32_t ft = sb + OFF_QT + tr * 32 + (((lane >> 4) ^ (tr >> 2)) & 1) * 16;
      const float g0 = __uint_as_float(lds32(sb + OFF_GATE + (64 * wg + 16 * w + g) * 4));
      const float g1 = __uint_as_float(lds32(sb + OFF_GATE + (64 * wg + 16 * w + 8 + g) * 4));
      const uint32_t ga = pack2(g0, g0), gb = pack2(g1, g1);
      const uint32_t na = pack2(1.f - g0, 1.f - g0), nb = pack2(1.f - g1, 1.f - g1);

      wg_wait<0>();
      pin<40>(acc);
      TSM(w == 0, 17 + wg);
      uint32_t pb[20];
#pragma unroll
      for (int j = 0; j < 10; j++) {
        pb[2 * j] = bmul(na, pack2(acc[4 * j], acc[4 * j + 1]));
        pb[2 * j + 1] = bmul(nb, pack2(acc[4 * j + 2], acc[4 * j + 3]));
        asm volatile("" : "+r"(pb[2 * j]), "+r"(pb[2 * j + 1]));
      }
      const uint32_t ya = sb + OFF_YT + wg * 10240 + ((lane >> 4) * 8 + (lane & 7)) * 128 +
                          (((2 * w + (((lane >> 3) & 1) ^ wg)) ^ (lane & 7)) << 4);
      uint32_t qf[20];
      mbar_wait(bars + 8 * B_QF, 0);
#pragma unroll
      for (int j = 0; j < 5; j++) ldsm4(qf + 4 * j, j < 4 ? fm + ((fx ^ (2 * j)) << 4) : ft);
      mbar_wait(bars + 8 * B_YFULL, 0);
      TSM(w == 0 && wg == 0, 19);
#pragma unroll
      for (int j = 0; j < 5; j++) {
        uint32_t y[4];
        ldsm4t(y, ya + 2048 * j);
#pragma unroll
        for (int i = 0; i < 4; i++) qf[4 * j + i] = badd(bmul((i & 1) ? gb : ga, bmul(qf[4 * j + i], y[i])), pb[4 * j + i]);
      }
#pragma unroll
      for (int j = 0; j < 5; j++) stsm4(j < 4 ? fm + ((fx ^ (2 * j)) << 4) : ft, qf + 4 * j);
      fence_async_smem();
      __syncwarp();
      if (lane == 0) {
        const int row = 64 * wg + 16 * w;
        asm volatile("cp.async.bulk.tensor.2d.global.shared::cta.bulk_group [%0, {%2, %3}], [%1];"
                     ::"l"(&m.om), "r"(sb + OFF_QS + row * 128), "r"(80 * hg), "r"(128 * r + row) : "memory");
        asm volatile("cp.async.bulk.tensor.2d.global.shared::cta.bulk_group [%0, {%2, %3}], [%1];"
                     ::"l"(&m.ot), "r"(sb + OFF_QT + row * 32), "r"(80 * hg + 64), "r"(128 * r + row) : "memory");
        asm volatile("cp.async.bulk.commit_group;\ncp.async.bulk.wait_group.read 0;" ::: "memory");
      }
      TSM(true, 40 + 4 * wg + w);
      if (ENDBAR) asm volatile("bar.sync 15, 256;" ::: "memory");
    }
  }
}

typedef CUresult (*EncodeFn)(CUtensorMap*, CUtensorMapDataType, cuuint32_t, void*, const cuuint64_t*, const cuuint64_t*,
                             const cuuint32_t*, const cuuint32_t*, CUtensorMapInterleave, CUtensorMapSwizzle,
                             CUtensorMapL2promotion, CUtensorMapFloatOOBfill);

void encode(EncodeFn fn, CUtensorMap* tm, const void* base, int rank, const cuuint64_t* dims, const cuuint64_t* strides,
            const cuuint32_t* box, CUtensorMapSwizzle swz) {
  const cuuint32_t ones[3] = {1, 1, 1};
  fn(tm, CU_TENSOR_MAP_DATA_TYPE_BFLOAT16, rank, const_cast<void*>(base), dims, strides, box, ones,
     CU_TENSOR_MAP_INTERLEAVE_NONE, swz, CU_TENSOR_MAP_L2_PROMOTION_L2_128B, CU_TENSOR_MAP_FLOAT_OOB_FILL_NONE);
}

}

extern "C" void kernel_launch(void* const* d_in, const int* in_sizes, int n_in, void* d_out, int out_size) {
  (void)in_sizes; (void)n_in; (void)out_size;
  Params p;
  p.q = (const __nv_bfloat16*)d_in[0];
  p.k = (const __nv_bfloat16*)d_in[1];
  p.v = (const __nv_bfloat16*)d_in[2];
  p.shift_k = (const __nv_bfloat16*)d_in[3];
  p.ssm_k = (const __nv_bfloat16*)d_in[4];
  p.ssm_D = (const __nv_bfloat16*)d_in[5];
  p.wqkv = (const __nv_bfloat16*)d_in[7];
  p.wo = (const __nv_bfloat16*)d_in[8];
  p.gate_w = (const __nv_bfloat16*)d_in[9];
  p.out = (__nv_bfloat16*)d_out;
  p.zero = 0;

  static EncodeFn fn = nullptr;
  static void *yaddr = nullptr, *uaddr = nullptr;
  if (!fn) {
    cudaDriverEntryPointQueryResult qr;
    void* f = nullptr;
    cudaGetDriverEntryPoint("cuTensorMapEncodeTiled", &f, cudaEnableDefault, &qr);
    fn = (EncodeFn)f;
    cudaGetSymbolAddress(&yaddr, g_Y);
    cudaGetSymbolAddress(&uaddr, g_U);
    cudaFuncSetAttribute(fused_kernel, cudaFuncAttributeMaxDynamicSharedMemorySize, SMEM_BYTES);
  }
  Maps m;
  {
    const cuuint64_t dims[3] = {640, 1024, 2}, st[2] = {2560, 1280};
    const cuuint32_t box[3] = {64, 64, 2};
    encode(fn, &m.x, p.q, 3, dims, st, box, CU_TENSOR_MAP_SWIZZLE_128B);
  }
  {
    const cuuint64_t dims[3] = {640, 640, 3}, st[2] = {3840, 1280};
    const cuuint32_t box[3] = {64, 64, 3}, boxt[3] = {16, 64, 3};
    encode(fn, &m.wm, p.wqkv, 3, dims, st, box, CU_TENSOR_MAP_SWIZZLE_128B);
    encode(fn, &m.wt, p.wqkv, 3, dims, st, boxt, CU_TENSOR_MAP_SWIZZLE_32B);
  }
  {
    const cuuint64_t dims[3] = {64, 2048, 10}, st[2] = {1280, 128};
    const cuuint32_t boxk[3] = {64, 35, 1}, boxv[3] = {64, 32, 1};
    encode(fn, &m.k, p.k, 3, dims, st, boxk, CU_TENSOR_MAP_SWIZZLE_128B);
    encode(fn, &m.v, p.v, 3, dims, st, boxv, CU_TENSOR_MAP_SWIZZLE_128B);
  }
  {
    const cuuint64_t dims[3] = {16, 640, 40}, st[2] = {1280, 32};
    const cuuint32_t box[3] = {16, 40, 5};
    encode(fn, &m.wo, p.wo, 3, dims, st, box, CU_TENSOR_MAP_SWIZZLE_32B);
  }
  {
    const cuuint64_t dims[2] = {2048, 640}, st[1] = {Y_PITCH * 16};
    const cuuint32_t box[2] = {64, 80};
    encode(fn, &m.y, yaddr, 2, dims, st, box, CU_TENSOR_MAP_SWIZZLE_128B);
    const cuuint64_t stu[1] = {U_PITCH * 16};
    const cuuint32_t boxu[2] = {32, 64};
    encode(fn, &m.u, uaddr, 2, dims, stu, boxu, CU_TENSOR_MAP_SWIZZLE_NONE);
  }
  {
    const cuuint64_t dims[2] = {640, 2048}, st[1] = {1280};
    const cuuint32_t bqm[2] = {64, 128}, bqt[2] = {16, 128}, bom[2] = {64, 16}, bot[2] = {16, 16};
    encode(fn, &m.qm, p.q, 2, dims, st, bqm, CU_TENSOR_MAP_SWIZZLE_128B);
    encode(fn, &m.qt, p.q, 2, dims, st, bqt, CU_TENSOR_MAP_SWIZZLE_32B);
    encode(fn, &m.om, p.out, 2, dims, st, bom, CU_TENSOR_MAP_SWIZZLE_128B);
    encode(fn, &m.ot, p.out, 2, dims, st, bot, CU_TENSOR_MAP_SWIZZLE_32B);
  }
  fused_kernel<<<NCTA, NTHR, SMEM_BYTES>>>(m, p);
}
```

```cpp
#include <cuda.h>
#include <cuda_bf16.h>
#include <cuda_runtime.h>
#include <stdint.h>

namespace {

constexpr int SEQ = 2048, DIM = 640, NCTA = 128, NTHR = 512;

#define TRIG_KB 9
#define KV_KB 2
#define DEV_EXIT 0
#define ATT_GATE 1
#define G_AFTER 0
#define FENCE_LO 0
#define FENCE_HI 0
#define PW1 2
#define PW2 1
#define ENDBAR 0
#define PAD_KB 0
#define Y_ALIAS 1
#define H_EARLY 1
#define NOMB 0
#define SRC_ROT 0
#define WAIT_NS 0
#define WB_TRIG B_USIG
#define G_POS 0
#define TAILF 1
#define T_ISSUE 384
#define T_PF 416
#define T_INIT 448
#define ATT_MERGE 0
#define BMAP 1
#define PRE2 1
#define KV_MIX 0
#define O_DEFER 0
#define TASK0 0x52
#define TASK1 0x3
#define TASK2 0x41
#define HALO_FIRST 1
#define PREV_EARLY 0
#define ACQ 0
#define U_TMA 0
#define U_GATE 0
#define RF_GATE 0
#define WO_TRIG B_WST
#define WL_TRIG B_WOP
#define WO_GATE 1

constexpr uint32_t STAGE_BYTES = 47104, ST_W = 16384, ST_WT = 40960;
constexpr uint32_t O_BYTES = 20480, WO_BYTES = 12800;
constexpr uint32_t OFF_OA = 0;
constexpr uint32_t OFF_QS = 3 * O_BYTES, OFF_QT = OFF_QS + 16384;
constexpr uint32_t OFF_WC = 81920;
constexpr uint32_t OFF_WA = 94720;
constexpr uint32_t OFF_GATE = 145920;
constexpr uint32_t OFF_TT = 146432;
constexpr uint32_t OFF_KVX = 148480;
constexpr uint32_t OFF_CH3 = 163840;
constexpr uint32_t CH_BYTES = 12288, U_BYTES = 4096;
constexpr uint32_t OFF_FT = 225280, OFF_GT = 229376;
constexpr uint32_t OFF_CH0 = 188416;
constexpr uint32_t OFF_KVS = OFF_CH0, KVS_V = 4480, KVS_BYTES = 8576;
constexpr uint32_t OFF_WS = OFF_WA;
__device__ __forceinline__ uint32_t off_us(int s) { return OFF_CH0 + 4096 * ((0x65320 >> (4 * s)) & 7); }
constexpr uint32_t OFF_YT = 163840;
constexpr uint32_t OFF_BAR = 231936;
constexpr uint32_t SMEM_BYTES = OFF_BAR + 512;

enum : uint32_t {
  B_FULL1 = 0, B_EMPTY1 = 4, B_S3 = 7, B_FULL2 = 52, B_EMPTY2 = 13, B_U = 8, B_GATE = 12, B_HA = 19, B_HB = 20,
  B_ATTN = 21, B_C34 = 22, B_CONV = 23, B_YFULL = 24, B_EPOCH = 25, B_PREP = 26, B_P1 = 27, B_LAST = 28,
  B_E3 = 29, B_OSIG = 30, B_WOP = 31, B_USIG = 32, B_WST = 33, B_KV = 34, B_KVD = 39, B_QF = 17, B_YST = 40,
  B_US = 45, B_YSIG = 50
};
constexpr uint32_t OFF_EPOCH = OFF_BAR + 8 * 51, OFF_D = OFF_BAR + 8 * 60;
__device__ __forceinline__ uint32_t off_o(int j) { return j < 4 ? OFF_OA + j * O_BYTES : j < 6 ? OFF_CH0 + (j - 4) * O_BYTES : OFF_OA + (j - 6) * O_BYTES; }
__device__ __forceinline__ uint32_t off_w(int j) { return j < 4 ? OFF_WA + j * WO_BYTES : j == 4 ? OFF_KVX : j == 5 ? OFF_WC : OFF_WA + (j - 6) * WO_BYTES; }
__device__ __forceinline__ int step_src(int hg, int j) { return SRC_ROT ? (hg + j) & 7 : j == 0 ? hg : j <= hg ? j - 1 : j; }
__device__ __forceinline__ bool tail_first(int hg) { return TAILF && (hg & 3) == 3; }
__device__ __forceinline__ uint32_t off_ch(int c) { return (c < 3 ? OFF_CH0 : OFF_CH3 - 3 * CH_BYTES) + c * CH_BYTES; }

#define U_PITCH 264
__device__ __align__(1024) uint4 g_U[DIM * U_PITCH];
__device__ uint4 g_O[NCTA * 1280];
#define g_Y g_U
constexpr int Y_PITCH = U_PITCH;
__device__ uint4 g_WO[64 * 800];
__device__ uint4 g_halo[NCTA * 2 * 7 * 32];
__device__ float g_gate[SEQ + PAD_KB * 256];
__device__ unsigned g_cnt[32 * (1 + 2 * 16 + 8 + NCTA)];
constexpr int C_LAUNCH = 0, C_PREP = 32, C_Y = 32 * 17, C_W = 32 * 33, C_O = 32 * 41;

#define TSM(cond, slot) do { } while (0)
#define TSIF(cond, slot) do { if (__LINE__ >= FENCE_LO && __LINE__ < FENCE_HI) sched_fence(); } while (0)
__device__ __forceinline__ void sched_fence() {
  asm volatile("{\n.reg .pred p;\n.reg .u32 c;\nmov.u32 c, %%clock;\nsetp.eq.u32 p, c, 0;\n@p st.shared.u32 [%0], c;\n}"
               ::"r"(1024 + OFF_EPOCH + 4) : "memory");
}
#define TS(slot) TSIF(true, slot)

struct Params {
  const __nv_bfloat16 *q, *k, *v, *shift_k, *ssm_k, *ssm_D, *wqkv, *wo, *gate_w;
  __nv_bfloat16* out;
  uint32_t zero;
};

#define POLL_NS 0
constexpr int SPIN_LIMIT = 1 << 17;

__device__ __forceinline__ void mbar_init(uint32_t bar, uint32_t count) {
  asm volatile("mbarrier.init.shared::cta.b64 [%0], %1;" ::"r"(bar), "r"(count) : "memory");
}
__device__ __forceinline__ void mbar_expect_tx(uint32_t bar, uint32_t bytes) {
  asm volatile("mbarrier.arrive.expect_tx.shared::cta.b64 _, [%0], %1;" ::"r"(bar), "r"(bytes) : "memory");
}
__device__ __forceinline__ void mbar_arrive(uint32_t bar) {
  asm volatile("mbarrier.arrive.shared::cta.b64 _, [%0];" ::"r"(bar) : "memory");
}
__device__ __forceinline__ void mbar_wait(uint32_t bar, uint32_t parity) {
  uint32_t ok;
  int spins = 0;
  do {
    if (WAIT_NS)
      asm volatile("{\n.reg .pred p;\nmbarrier.try_wait.parity.shared::cta.b64 p, [%1], %2, %3;\nselp.b32 %0, 1, 0, p;\n}"
                   : "=r"(ok) : "r"(bar), "r"(parity), "r"(WAIT_NS) : "memory");
    else
      asm volatile("{\n.reg .pred p;\nmbarrier.try_wait.parity.shared::cta.b64 p, [%1], %2;\nselp.b32 %0, 1, 0, p;\n}"
                   : "=r"(ok) : "r"(bar), "r"(parity) : "memory");
    if (++spins > SPIN_LIMIT) break;
  } while (!ok);
}
__device__ __forceinline__ unsigned flag_read(const unsigned* p) {
  unsigned v;
  asm volatile("ld.relaxed.gpu.global.u32 %0, [%1];" : "=r"(v) : "l"(p) : "memory");
  return v;
}
__device__ __forceinline__ void flag_poll(const unsigned* p, unsigned target) {
  unsigned v;
  int spins = 0;
  do {
    if (POLL_NS && spins) __nanosleep(POLL_NS);
    asm volatile("ld.relaxed.gpu.global.u32 %0, [%1];" : "=r"(v) : "l"(p) : "memory");
    if (++spins > SPIN_LIMIT) break;
  } while ((int)(v - target) < 0);
}
__device__ __forceinline__ void flag_wait(const unsigned* p, unsigned target) {
  flag_poll(p, target);
  if (ACQ) asm volatile("fence.acquire.gpu;\nfence.proxy.async.global;" ::: "memory");
}
__device__ __forceinline__ void flag_signal(unsigned* p, int n, int lane) {
  if (lane == 0) asm volatile("fence.release.gpu;" ::: "memory");
  __syncwarp();
  if (lane < n) asm volatile("red.relaxed.gpu.global.add.u32 [%0], 1;" ::"l"(p + 32 * lane) : "memory");
}
__device__ __forceinline__ void flag_bump(unsigned* p) {
  asm volatile("red.relaxed.gpu.global.add.u32 [%0], 1;" ::"l"(p) : "memory");
}
__device__ __forceinline__ void fence_async_smem() { asm volatile("fence.proxy.async.shared::cta;" ::: "memory"); }
__device__ __forceinline__ void wg_sync(int id) { asm volatile("bar.sync %0, 128;" ::"r"(id) : "memory"); }

__device__ __forceinline__ void tma_2d(uint32_t dst, const CUtensorMap* tm, int c0, int c1, uint32_t bar) {
  asm volatile("cp.async.bulk.tensor.2d.shared::cluster.global.mbarrier::complete_tx::bytes [%0], [%1, {%3, %4}], [%2];"
               ::"r"(dst), "l"(tm), "r"(bar), "r"(c0), "r"(c1) : "memory");
}
__device__ __forceinline__ void tma_3d(uint32_t dst, const CUtensorMap* tm, int c0, int c1, int c2, uint32_t bar) {
  asm volatile("cp.async.bulk.tensor.3d.shared::cluster.global.mbarrier::complete_tx::bytes [%0], [%1, {%3, %4, %5}], [%2];"
               ::"r"(dst), "l"(tm), "r"(bar), "r"(c0), "r"(c1), "r"(c2) : "memory");
}
__device__ __forceinline__ void bulk_load(uint32_t dst, const void* src, uint32_t bytes, uint32_t bar) {
  asm volatile("cp.async.bulk.shared::cluster.global.mbarrier::complete_tx::bytes [%0], [%1], %2, [%3];"
               ::"r"(dst), "l"(src), "r"(bytes), "r"(bar) : "memory");
}
__device__ __forceinline__ void tm_prefetch(const CUtensorMap* tm) {
  asm volatile("prefetch.tensormap [%0];" ::"l"(tm) : "memory");
}

__device__ __forceinline__ void wg_fence() { asm volatile("wgmma.fence.sync.aligned;" ::: "memory"); }
__device__ __forceinline__ void wg_commit() { asm volatile("wgmma.commit_group.sync.aligned;" ::: "memory"); }
template <int N> __device__ __forceinline__ void wg_wait() { asm volatile("wgmma.wait_group.sync.aligned %0;" ::"n"(N) : "memory"); }
__device__ __forceinline__ uint32_t desc_lo(uint32_t addr, uint32_t lbo) { return ((addr & 0x3FFFF) >> 4) | ((lbo >> 4) << 16); }
constexpr uint32_t desc_hi(uint32_t sbo, uint32_t swz) { return (sbo >> 4) | (swz << 30); }
constexpr uint32_t HI_SW128 = desc_hi(1024, 1), HI_SW64 = desc_hi(512, 2), HI_SW32 = desc_hi(256, 3), HI_NONE = desc_hi(128, 0);
template <int N> __device__ __forceinline__ void pin(float* d) {
#pragma unroll
  for (int i = 0; i < N; i++) asm volatile("" : "+f"(d[i])::"memory");
}

__device__ __forceinline__ uint32_t lds32(uint32_t a) {
  uint32_t v;
  asm volatile("ld.volatile.shared.u32 %0, [%1];" : "=r"(v) : "r"(a) : "memory");
  return v;
}
__device__ __forceinline__ uint4 ldg128(const void* a) {
  uint4 v;
  asm volatile("ld.global.nc.v4.u32 {%0, %1, %2, %3}, [%4];" : "=r"(v.x), "=r"(v.y), "=r"(v.z), "=r"(v.w) : "l"(a) : "memory");
  return v;
}
__device__ __forceinline__ uint2 ldg64(const void* a) {
  uint2 v;
  asm volatile("ld.global.nc.v2.u32 {%0, %1}, [%2];" : "=r"(v.x), "=r"(v.y) : "l"(a) : "memory");
  return v;
}
__device__ __forceinline__ void ldsm4(uint32_t* r, uint32_t a) {
  asm volatile("ldmatrix.sync.aligned.m8n8.x4.shared.b16 {%0, %1, %2, %3}, [%4];"
               : "=r"(r[0]), "=r"(r[1]), "=r"(r[2]), "=r"(r[3]) : "r"(a) : "memory");
}
__device__ __forceinline__ void ldsm4t(uint32_t* r, uint32_t a) {
  asm volatile("ldmatrix.sync.aligned.m8n8.x4.trans.shared.b16 {%0, %1, %2, %3}, [%4];"
               : "=r"(r[0]), "=r"(r[1]), "=r"(r[2]), "=r"(r[3]) : "r"(a) : "memory");
}
__device__ __forceinline__ uint2 lds64(uint32_t a) {
  uint2 v;
  asm volatile("ld.shared.v2.u32 {%0, %1}, [%2];" : "=r"(v.x), "=r"(v.y) : "r"(a) : "memory");
  return v;
}
__device__ __forceinline__ uint4 lds128(uint32_t a) {
  uint4 v;
  asm volatile("ld.shared.v4.u32 {%0, %1, %2, %3}, [%4];" : "=r"(v.x), "=r"(v.y), "=r"(v.z), "=r"(v.w) : "r"(a) : "memory");
  return v;
}
__device__ __forceinline__ void sts128(uint32_t a, uint32_t x, uint32_t y, uint32_t z, uint32_t w) {
  asm volatile("st.shared.v4.u32 [%0], {%1, %2, %3, %4};" ::"r"(a), "r"(x), "r"(y), "r"(z), "r"(w) : "memory");
}
__device__ __forceinline__ void stsm4(uint32_t a, const uint32_t* r) {
  asm volatile("stmatrix.sync.aligned.m8n8.x4.shared.b16 [%0], {%1, %2, %3, %4};" ::"r"(a), "r"(r[0]), "r"(r[1]), "r"(r[2]), "r"(r[3]) : "memory");
}
__device__ __forceinline__ void stsm4t(uint32_t a, const uint32_t* r) {
  asm volatile("stmatrix.sync.aligned.m8n8.x4.trans.shared.b16 [%0], {%1, %2, %3, %4};" ::"r"(a), "r"(r[0]), "r"(r[1]), "r"(r[2]), "r"(r[3]) : "memory");
}
__device__ __forceinline__ uint32_t pack2(float lo, float hi) {
  uint32_t r;
  asm("cvt.rn.bf16x2.f32 %0, %1, %2;" : "=r"(r) : "f"(hi), "f"(lo));
  return r;
}
__device__ __forceinline__ uint32_t movm(uint32_t a) {
  uint32_t d;
  asm volatile("movmatrix.sync.aligned.m8n8.trans.b16 %0, %1;" : "=r"(d) : "r"(a));
  return d;
}
__device__ __forceinline__ uint32_t bmul(uint32_t a, uint32_t b) {
  uint32_t d;
  asm("mul.rn.bf16x2 %0, %1, %2;" : "=r"(d) : "r"(a), "r"(b));
  return d;
}
__device__ __forceinline__ uint32_t badd(uint32_t a, uint32_t b) {
  uint32_t d;
  asm("add.rn.bf16x2 %0, %1, %2;" : "=r"(d) : "r"(a), "r"(b));
  return d;
}
__device__ __forceinline__ uint32_t bfma(uint32_t a, uint32_t b, uint32_t c) {
  uint32_t d;
  asm("fma.rn.bf16x2 %0, %1, %2, %3;" : "=r"(d) : "r"(a), "r"(b), "r"(c));
  return d;
}
__device__ __forceinline__ float bf_lo(uint32_t x) { return __uint_as_float(x << 16); }
__device__ __forceinline__ float bf_hi(uint32_t x) { return __uint_as_float(x & 0xFFFF0000u); }
__device__ __forceinline__ float ex2(float x) {
  float y;
  asm("ex2.approx.ftz.f32 %0, %1;" : "=f"(y) : "f"(x));
  return y;
}
__device__ __forceinline__ float rcp(float x) {
  float y;
  asm("rcp.approx.ftz.f32 %0, %1;" : "=f"(y) : "f"(x));
  return y;
}
__device__ __forceinline__ void mma16816(float* d, uint32_t a0, uint32_t a1, uint32_t a2, uint32_t a3, uint32_t b0, uint32_t b1) {
  asm volatile("mma.sync.aligned.m16n8k16.row.col.f32.bf16.bf16.f32 {%0, %1, %2, %3}, {%4, %5, %6, %7}, {%8, %9}, {%0, %1, %2, %3};"
               : "+f"(d[0]), "+f"(d[1]), "+f"(d[2]), "+f"(d[3])
               : "r"(a0), "r"(a1), "r"(a2), "r"(a3), "r"(b0), "r"(b1));
}
__device__ __forceinline__ void mma1688(float* d, uint32_t a0, uint32_t a1, uint32_t b0) {
  asm volatile("mma.sync.aligned.m16n8k8.row.col.f32.bf16.bf16.f32 {%0, %1, %2, %3}, {%4, %5}, {%6}, {%0, %1, %2, %3};"
               : "+f"(d[0]), "+f"(d[1]), "+f"(d[2]), "+f"(d[3])
               : "r"(a0), "r"(a1), "r"(b0));
}

template <int N> struct WgRS;
template <int N> struct WgSST;
template <> struct WgRS<32> {
  template <uint32_t HB>
  static __device__ __forceinline__ void mma(float* d, const uint32_t* a, uint32_t db) {
    asm volatile("{\n.reg .pred p;\n.reg .b64 db;\nsetp.ne.b32 p, %22, 0;\n"
      "mov.b64 db, {%20, %21};\n"
      "wgmma.mma_async.sync.aligned.m64n32k16.f32.bf16.bf16 {"
      "%0, %1, %2, %3, %4, %5, %6, %7, %8, %9, %10, %11, %12, %13, %14, %15"
      "}, {%16, %17, %18, %19}, db, p, 1, 1, 1;\n}\n"
      : "+f"(d[0]), "+f"(d[1]), "+f"(d[2]), "+f"(d[3]), "+f"(d[4]), "+f"(d[5]), "+f"(d[6]), "+f"(d[7]),
        "+f"(d[8]), "+f"(d[9]), "+f"(d[10]), "+f"(d[11]), "+f"(d[12]), "+f"(d[13]), "+f"(d[14]), "+f"(d[15])
      : "r"(a[0]), "r"(a[1]), "r"(a[2]), "r"(a[3]), "r"(db), "n"(HB), "n"(1));
  }
  template <uint32_t HB>
  static __device__ __forceinline__ void set(float* d, const uint32_t* a, uint32_t db) {
    asm volatile("{\n.reg .pred p;\n.reg .b64 db;\nsetp.ne.b32 p, %22, 0;\n"
      "mov.b64 db, {%20, %21};\n"
      "wgmma.mma_async.sync.aligned.m64n32k16.f32.bf16.bf16 {"
      "%0, %1, %2, %3, %4, %5, %6, %7, %8, %9, %10, %11, %12, %13, %14, %15"
      "}, {%16, %17, %18, %19}, db, p, 1, 1, 1;\n}\n"
      : "=f"(d[0]), "=f"(d[1]), "=f"(d[2]), "=f"(d[3]), "=f"(d[4]), "=f"(d[5]), "=f"(d[6]), "=f"(d[7]),
        "=f"(d[8]), "=f"(d[9]), "=f"(d[10]), "=f"(d[11]), "=f"(d[12]), "=f"(d[13]), "=f"(d[14]), "=f"(d[15])
      : "r"(a[0]), "r"(a[1]), "r"(a[2]), "r"(a[3]), "r"(db), "n"(HB), "n"(0));
  }
};
template <> struct WgRS<64> {
  template <uint32_t HB>
  static __device__ __forceinline__ void mma(float* d, const uint32_t* a, uint32_t db) {
    asm volatile("{\n.reg .pred p;\n.reg .b64 db;\nsetp.ne.b32 p, %38, 0;\n"
      "mov.b64 db, {%36, %37};\n"
      "wgmma.mma_async.sync.aligned.m64n64k16.f32.bf16.bf16 {"
      "%0, %1, %2, %3, %4, %5, %6, %7, %8, %9, %10, %11, %12, %13, %14, %15, "
      "%16, %17, %18, %19, %20, %21, %22, %23, %24, %25, %26, %27, %28, %29, %30, %31"
      "}, {%32, %33, %34, %35}, db, p, 1, 1, 1;\n}\n"
      : "+f"(d[0]), "+f"(d[1]), "+f"(d[2]), "+f"(d[3]), "+f"(d[4]), "+f"(d[5]), "+f"(d[6]), "+f"(d[7]),
        "+f"(d[8]), "+f"(d[9]), "+f"(d[10]), "+f"(d[11]), "+f"(d[12]), "+f"(d[13]), "+f"(d[14]), "+f"(d[15]),
        "+f"(d[16]), "+f"(d[17]), "+f"(d[18]), "+f"(d[19]), "+f"(d[20]), "+f"(d[21]), "+f"(d[22]), "+f"(d[23]),
        "+f"(d[24]), "+f"(d[25]), "+f"(d[26]), "+f"(d[27]), "+f"(d[28]), "+f"(d[29]), "+f"(d[30]), "+f"(d[31])
      : "r"(a[0]), "r"(a[1]), "r"(a[2]), "r"(a[3]), "r"(db), "n"(HB), "n"(1));
  }
  template <uint32_t HB>
  static __device__ __forceinline__ void set(float* d, const uint32_t* a, uint32_t db) {
    asm volatile("{\n.reg .pred p;\n.reg .b64 db;\nsetp.ne.b32 p, %38, 0;\n"
      "mov.b64 db, {%36, %37};\n"
      "wgmma.mma_async.sync.aligned.m64n64k16.f32.bf16.bf16 {"
      "%0, %1, %2, %3, %4, %5, %6, %7, %8, %9, %10, %11, %12, %13, %14, %15, "
      "%16, %17, %18, %19, %20, %21, %22, %23, %24, %25, %26, %27, %28, %29, %30, %31"
      "}, {%32, %33, %34, %35}, db, p, 1, 1, 1;\n}\n"
      : "=f"(d[0]), "=f"(d[1]), "=f"(d[2]), "=f"(d[3]), "=f"(d[4]), "=f"(d[5]), "=f"(d[6]), "=f"(d[7]),
        "=f"(d[8]), "=f"(d[9]), "=f"(d[10]), "=f"(d[11]), "=f"(d[12]), "=f"(d[13]), "=f"(d[14]), "=f"(d[15]),
        "=f"(d[16]), "=f"(d[17]), "=f"(d[18]), "=f"(d[19]), "=f"(d[20]), "=f"(d[21]), "=f"(d[22]), "=f"(d[23]),
        "=f"(d[24]), "=f"(d[25]), "=f"(d[26]), "=f"(d[27]), "=f"(d[28]), "=f"(d[29]), "=f"(d[30]), "=f"(d[31])
      : "r"(a[0]), "r"(a[1]), "r"(a[2]), "r"(a[3]), "r"(db), "n"(HB), "n"(0));
  }
};
template <> struct WgSST<48> {
  template <uint32_t HA, uint32_t HB>
  static __device__ __forceinline__ void mma(float* d, uint32_t da, uint32_t db, int sc) {
    asm volatile("{\n.reg .pred p;\n.reg .b64 da, db;\nsetp.ne.b32 p, %28, 0;\n"
      "mov.b64 da, {%24, %25};\nmov.b64 db, {%26, %27};\n"
      "wgmma.mma_async.sync.aligned.m64n48k16.f32.bf16.bf16 {"
      "%0, %1, %2, %3, %4, %5, %6, %7, %8, %9, %10, %11, %12, %13, %14, %15, "
      "%16, %17, %18, %19, %20, %21, %22, %23"
      "}, da, db, p, 1, 1, 0, 1;\n}\n"
      : "+f"(d[0]), "+f"(d[1]), "+f"(d[2]), "+f"(d[3]), "+f"(d[4]), "+f"(d[5]), "+f"(d[6]), "+f"(d[7]),
        "+f"(d[8]), "+f"(d[9]), "+f"(d[10]), "+f"(d[11]), "+f"(d[12]), "+f"(d[13]), "+f"(d[14]), "+f"(d[15]),
        "+f"(d[16]), "+f"(d[17]), "+f"(d[18]), "+f"(d[19]), "+f"(d[20]), "+f"(d[21]), "+f"(d[22]), "+f"(d[23])
      : "r"(da), "n"(HA), "r"(db), "n"(HB), "r"(sc));
  }
};
template <> struct WgSST<80> {
  template <uint32_t HA, uint32_t HB>
  static __device__ __forceinline__ void mma(float* d, uint32_t da, uint32_t db, int sc) {
    asm volatile("{\n.reg .pred p;\n.reg .b64 da, db;\nsetp.ne.b32 p, %44, 0;\n"
      "mov.b64 da, {%40, %41};\nmov.b64 db, {%42, %43};\n"
      "wgmma.mma_async.sync.aligned.m64n80k16.f32.bf16.bf16 {"
      "%0, %1, %2, %3, %4, %5, %6, %7, %8, %9, %10, %11, %12, %13, %14, %15, "
      "%16, %17, %18, %19, %20, %21, %22, %23, %24, %25, %26, %27, %28, %29, %30, %31, "
      "%32, %33, %34, %35, %36, %37, %38, %39"
      "}, da, db, p, 1, 1, 0, 1;\n}\n"
      : "+f"(d[0]), "+f"(d[1]), "+f"(d[2]), "+f"(d[3]), "+f"(d[4]), "+f"(d[5]), "+f"(d[6]), "+f"(d[7]),
        "+f"(d[8]), "+f"(d[9]), "+f"(d[10]), "+f"(d[11]), "+f"(d[12]), "+f"(d[13]), "+f"(d[14]), "+f"(d[15]),
        "+f"(d[16]), "+f"(d[17]), "+f"(d[18]), "+f"(d[19]), "+f"(d[20]), "+f"(d[21]), "+f"(d[22]), "+f"(d[23]),
        "+f"(d[24]), "+f"(d[25]), "+f"(d[26]), "+f"(d[27]), "+f"(d[28]), "+f"(d[29]), "+f"(d[30]), "+f"(d[31]),
        "+f"(d[32]), "+f"(d[33]), "+f"(d[34]), "+f"(d[35]), "+f"(d[36]), "+f"(d[37]), "+f"(d[38]), "+f"(d[39])
      : "r"(da), "n"(HA), "r"(db), "n"(HB), "r"(sc));
  }
};
template <> struct WgSST<192> {
  template <uint32_t HA, uint32_t HB>
  static __device__ __forceinline__ void mma(float* d, uint32_t da, uint32_t db, int sc) {
    asm volatile("{\n.reg .pred p;\n.reg .b64 da, db;\nsetp.ne.b32 p, %100, 0;\n"
      "mov.b64 da, {%96, %97};\nmov.b64 db, {%98, %99};\n"
      "wgmma.mma_async.sync.aligned.m64n192k16.f32.bf16.bf16 {"
      "%0, %1, %2, %3, %4, %5, %6, %7, %8, %9, %10, %11, %12, %13, %14, %15, "
      "%16, %17, %18, %19, %20, %21, %22, %23, %24, %25, %26, %27, %28, %29, %30, %31, "
      "%32, %33, %34, %35, %36, %37, %38, %39, %40, %41, %42, %43, %44, %45, %46, %47, "
      "%48, %49, %50, %51, %52, %53, %54, %55, %56, %57, %58, %59, %60, %61, %62, %63, "
      "%64, %65, %66, %67, %68, %69, %70, %71, %72, %73, %74, %75, %76, %77, %78, %79, "
      "%80, %81, %82, %83, %84, %85, %86, %87, %88, %89, %90, %91, %92, %93, %94, %95"
      "}, da, db, p, 1, 1, 0, 1;\n}\n"
      : "+f"(d[0]), "+f"(d[1]), "+f"(d[2]), "+f"(d[3]), "+f"(d[4]), "+f"(d[5]), "+f"(d[6]), "+f"(d[7]),
        "+f"(d[8]), "+f"(d[9]), "+f"(d[10]), "+f"(d[11]), "+f"(d[12]), "+f"(d[13]), "+f"(d[14]), "+f"(d[15]),
        "+f"(d[16]), "+f"(d[17]), "+f"(d[18]), "+f"(d[19]), "+f"(d[20]), "+f"(d[21]), "+f"(d[22]), "+f"(d[23]),
        "+f"(d[24]), "+f"(d[25]), "+f"(d[26]), "+f"(d[27]), "+f"(d[28]), "+f"(d[29]), "+f"(d[30]), "+f"(d[31]),
        "+f"(d[32]), "+f"(d[33]), "+f"(d[34]), "+f"(d[35]), "+f"(d[36]), "+f"(d[37]), "+f"(d[38]), "+f"(d[39]),
        "+f"(d[40]), "+f"(d[41]), "+f"(d[42]), "+f"(d[43]), "+f"(d[44]), "+f"(d[45]), "+f"(d[46]), "+f"(d[47]),
        "+f"(d[48]), "+f"(d[49]), "+f"(d[50]), "+f"(d[51]), "+f"(d[52]), "+f"(d[53]), "+f"(d[54]), "+f"(d[55]),
        "+f"(d[56]), "+f"(d[57]), "+f"(d[58]), "+f"(d[59]), "+f"(d[60]), "+f"(d[61]), "+f"(d[62]), "+f"(d[63]),
        "+f"(d[64]), "+f"(d[65]), "+f"(d[66]), "+f"(d[67]), "+f"(d[68]), "+f"(d[69]), "+f"(d[70]), "+f"(d[71]),
        "+f"(d[72]), "+f"(d[73]), "+f"(d[74]), "+f"(d[75]), "+f"(d[76]), "+f"(d[77]), "+f"(d[78]), "+f"(d[79]),
        "+f"(d[80]), "+f"(d[81]), "+f"(d[82]), "+f"(d[83]), "+f"(d[84]), "+f"(d[85]), "+f"(d[86]), "+f"(d[87]),
        "+f"(d[88]), "+f"(d[89]), "+f"(d[90]), "+f"(d[91]), "+f"(d[92]), "+f"(d[93]), "+f"(d[94]), "+f"(d[95])
      : "r"(da), "n"(HA), "r"(db), "n"(HB), "r"(sc));
  }
};

struct FftConst {
  uint32_t f[2][4], fi[4][4];
  uint32_t ta[2][2], tb[2][2];
};
__device__ __forceinline__ void cis(int m, float scale, float& c, float& s) {
  const float a = (float)m * (-6.283185307179586f * scale);
  c = __cosf(a);
  s = __sinf(a);
}
__device__ __forceinline__ void fft_tables(uint32_t (&v)[12], int tw) {
  const int row = tw >> 2, ch = tw & 3;
#pragma unroll
  for (int i = 0; i < 4; i++) {
    float c[2], s[2], x[2];
#pragma unroll
    for (int e = 0; e < 2; e++) {
      cis((((32 * (8 * ch + 2 * i + e) + 15) * (4 * row - 63) + 2048) & 4095) - 2048, 1.f / 4096, c[e], s[e]);
      float gc, gs;
      cis((((row & 15) * (8 * (ch & 1) + 2 * i + e) + 8) & 15) - 8, 1.f / 16, gc, gs);
      x[e] = (row >> 4) == (ch >> 1) ? gc : (ch >> 1) ? gs : -gs;
    }
    v[i] = pack2(c[0] * 0.125f, c[1] * 0.125f);
    v[4 + i] = pack2(s[0] * 0.125f, s[1] * 0.125f);
    v[8 + i] = pack2(x[0], x[1]);
  }
#pragma unroll
  for (int i = 0; i < 12; i++) asm volatile("" : "+r"(v[i]));
}
__device__ __forceinline__ void fft_tables_store(const uint32_t (&v)[12], uint32_t sb, int tw) {
  const int row = tw >> 2;
  const uint32_t x = ((tw ^ (row >> 1)) & 3) << 4, a = sb + OFF_FT + (16 * (row >> 3) + (row & 7)) * 64 + x;
  sts128(a, v[0], v[1], v[2], v[3]);
  sts128(a + 512, v[4], v[5], v[6], v[7]);
  sts128(sb + OFF_GT + row * 64 + x, v[8], v[9], v[10], v[11]);
}
__device__ __forceinline__ void fft_twiddles(uint32_t (&v)[2], int tw) {
  float a[2], s[2];
#pragma unroll
  for (int i = 0; i < 2; i++) {
    float c;
    cis((2 * (2 * (tw & 3) + i) - 15) * (4 * (tw >> 2) - 63), 1.f / 4096, c, s[i]);
    a[i] = __fdividef(-s[i], 1.f + c);
  }
  v[0] = pack2(a[0], a[1]);
  v[1] = pack2(s[0], s[1]);
  asm volatile("" : "+r"(v[0]), "+r"(v[1]));
}
__device__ __forceinline__ void fft_matrices(FftConst& k, uint32_t sb, int w, int lane) {
  const uint32_t x = (lane >> 1) & 3;
  const uint2 t0 = lds64(sb + OFF_TT + 256 * w + 8 * lane), t1 = lds64(sb + OFF_TT + 256 * w + 8 * (lane ^ 3));
  k.ta[0][0] = t0.x;
  k.tb[0][0] = t0.y;
  k.ta[1][1] = __byte_perm(t1.x, 0, 0x1032);
  k.tb[1][1] = __byte_perm(t1.y, 0, 0x1032);
#pragma unroll
  for (int j = 0; j < 2; j++) {
    k.ta[1 - j][j] = k.ta[j][j] ^ 0x80008000u;
    k.tb[1 - j][j] = k.tb[j][j] ^ 0x80008000u;
    asm volatile("" : "+r"(k.ta[0][j]), "+r"(k.tb[0][j]), "+r"(k.ta[1][j]), "+r"(k.tb[1][j]));
  }
#pragma unroll
  for (int i = 0; i < 2; i++) {
    ldsm4(k.f[i], sb + OFF_FT + (16 * w + (lane & 15)) * 64 + (((2 * i + (lane >> 4)) ^ x) << 4));
    ldsm4t(k.fi[i], sb + OFF_FT + (32 * i + lane) * 64 + ((w ^ x) << 4));
#pragma unroll
    for (int j = 0; j < 4; j++) {
      k.fi[2 + i][j] = (j & 1) ? k.fi[i][j - 1] ^ 0x80008000u : k.fi[i][j + 1];
      asm volatile("" : "+r"(k.fi[2 + i][j]));
    }
  }
}
__device__ __forceinline__ void rot(uint32_t& x, uint32_t& y, uint32_t a, uint32_t b) {
  x = bfma(a, y, x);
  y = bfma(b, x, y);
  x = bfma(a, y, x);
}
__device__ __forceinline__ void twiddle_fwd(uint32_t (&a)[4][4], float* d, const FftConst& k) {
#pragma unroll
  for (int q = 0; q < 4; q++)
#pragma unroll
    for (int j = 0; j < 2; j++) {
      const float* x = d + 8 * q + 4 * j;
      uint32_t re = pack2(x[0], x[1]), im = pack2(x[2], x[3]);
      rot(re, im, k.ta[0][j], k.tb[0][j]);
      a[q & 2][2 * j + (q & 1)] = re;
      a[(q & 2) + 1][2 * j + (q & 1)] = im;
    }
}
__device__ __forceinline__ void g_step(float* d, const uint32_t (&a)[4][4], uint32_t dre, uint32_t dim) {
  WgRS<32>::set<HI_SW64>(d, a[0], dre);
  WgRS<32>::set<HI_SW64>(d + 16, a[2], dre);
  WgRS<32>::mma<HI_SW64>(d, a[1], dim);
  WgRS<32>::mma<HI_SW64>(d + 16, a[3], dim);
  wg_commit();
}

__device__ __forceinline__ void conv_channel(const FftConst& k, uint32_t sb, int c, int wg, int w, int lane) {
  const uint32_t cb = sb + off_ch(c), bars = sb + OFF_BAR;
  const uint32_t du = desc_lo(cb, 1024), dg = desc_lo(sb + OFF_GT, 16), dz = desc_lo(cb + U_BYTES, 16);
  float U[32], H[32];
  uint32_t a[4][4], e[4][4];
  const float dv = __uint_as_float(lds32(sb + OFF_D + 4 * c));
  wg_fence();
  WgRS<64>::set<HI_SW32>(H, k.f[0], du + 256);
  WgRS<64>::mma<HI_SW32>(H, k.f[1], du + 256 + 32);
  wg_commit();
  wg_wait<0>();
  pin<32>(H);
  twiddle_fwd(a, H, k);
  if (ATT_GATE && H_EARLY) mbar_wait(bars + 8 * B_ATTN, 0);
  mbar_wait(bars + 8 * (B_U + (c < 3 ? c : 3)), 0);
  TSM(w == 0 && c < 3, 7 + wg);
  wg_fence();
  WgRS<64>::set<HI_SW32>(U, k.f[0], du);
  WgRS<64>::mma<HI_SW32>(U, k.f[1], du + 32);
  wg_commit();
  g_step(H, a, dg, dg + 64);
  wg_wait<1>();
  pin<32>(U);
  twiddle_fwd(e, U, k);
  wg_fence();
  g_step(U, e, dg, dg + 64);
  wg_wait<0>();
  pin<32>(U);
  pin<32>(H);
#pragma unroll
  for (int j = 0; j < 2; j++) {
    float pr[4][2], pi[4][2];
#pragma unroll
    for (int x = 0; x < 2; x++) {
      H[4 * j + x] += dv;
#pragma unroll
      for (int m = 0; m < 4; m++) {
#pragma unroll
        for (int q = 0; q <= m; q++) {
          const int ih = 16 * (q >> 1) + 2 * (q & 1) + 4 * j + x, iu = 16 * ((m - q) >> 1) + 2 * ((m - q) & 1) + 4 * j + x;
          pr[m][x] = q ? fmaf(H[ih], U[iu], pr[m][x]) : H[ih] * U[iu];
          pi[m][x] = q ? fmaf(H[ih], U[iu + 8], pi[m][x]) : H[ih] * U[iu + 8];
          pr[m][x] = fmaf(-H[ih + 8], U[iu + 8], pr[m][x]);
          pi[m][x] = fmaf(H[ih + 8], U[iu], pi[m][x]);
        }
      }
    }
#pragma unroll
    for (int m = 0; m < 4; m++) {
      a[m & 2][2 * j + (m & 1)] = pack2(pr[m][0], pr[m][1]);
      a[(m & 2) + 1][2 * j + (m & 1)] = pack2(pi[m][0], pi[m][1]);
    }
  }
  wg_fence();
  g_step(U, a, dg + 64, dg);
  const uint32_t za = cb + U_BYTES + (8 * w + (lane & 7)) * 128 + (((lane >> 3) ^ (lane & 7)) << 4);
  const uint32_t ya = cb + (lane >> 4) * 1024 + (8 * w + (lane & 7)) * 32 + ((((lane >> 3) ^ (lane >> 2)) & 1) << 4);
  wg_sync(1 + wg);
  wg_wait<0>();
  pin<32>(U);
  TSIF(w == 0, 80 + c);
#pragma unroll
  for (int p = 0; p < 2; p++) {
#pragma unroll
    for (int i = 0; i < 4; i++) {
      const int j = i & 1;
      const float* x = U + 16 * p + 4 * j + (i & 2);
      e[p][i] = pack2(x[8], x[9]);
      e[2 + p][i] = pack2(x[0], x[1]);
      rot(e[p][i], e[2 + p][i], k.ta[1][j], k.tb[1][j]);
    }
    stsm4(za ^ (64 * p), e[p]);
    stsm4((za ^ (64 * p)) + 4096, e[2 + p]);
  }
  fence_async_smem();
  wg_sync(1 + wg);
  wg_fence();
  WgRS<64>::set<HI_SW128>(H, k.fi[0], dz);
#pragma unroll
  for (int ks = 1; ks < 4; ks++) WgRS<64>::mma<HI_SW128>(H, k.fi[ks], dz + 128 * ks);
  wg_commit();
  wg_wait<0>();
  pin<32>(H);
  TSIF(w == 0, 88 + c);
#pragma unroll
  for (int j = 0; j < 8; j++)
    a[j >> 2][j & 3] = j < 2 ? pack2(H[4 * j], H[4 * j + 1]) : pack2(H[4 * j] + H[4 * j - 6], H[4 * j + 1] + H[4 * j - 5]);
  stsm4(ya, a[0]);
  stsm4(ya + 2048, a[1]);
  fence_async_smem();
  __syncwarp();
}

__device__ __forceinline__ void prep_slab(uint4* res, const uint2* sw, uint32_t sb, int slab, int w, int lane) {
  const int t = lane & 3, tp = (lane & 7) >> 1, pos = 8 * tp + 2 * (((lane >> 3) + tp) & 3) + (lane & 1);
  const uint32_t base = sb + OFF_KVS + slab * KVS_BYTES + pos * 128;
  uint32_t kk[2][4][4], vv[2][4];
  mbar_wait(sb + OFF_BAR + 8 * (B_KV + slab), 0);
#pragma unroll
  for (int h = 0; h < 2; h++) {
#pragma unroll
    for (int j = 0; j < 4; j++) {
      const uint32_t a = base + 128 * j;
      ldsm4t(kk[h][j], a + (((w + 4 * h) ^ ((a >> 7) & 7)) << 4));
    }
    const uint32_t a = base + KVS_V;
    ldsm4t(vv[h], a + (((w + 4 * h) ^ ((a >> 7) & 7)) << 4));
  }
#pragma unroll
  for (int h = 0; h < 2; h++) {
    uint32_t (&k)[4][4] = kk[h];
    uint32_t (&v)[4] = vv[h];
    const uint32_t w0 = __byte_perm(sw[h].x, 0, 0x1010), w1 = __byte_perm(sw[h].x, 0, 0x3232);
    const uint32_t w2 = __byte_perm(sw[h].y, 0, 0x1010), w3 = __byte_perm(sw[h].y, 0, 0x3232);
#pragma unroll
    for (int m = 0; m < 4; m++)
      v[m] = bmul(badd(badd(badd(bmul(k[0][m], w3), bmul(k[1][m], w2)), bmul(k[2][m], w1)), bmul(k[3][m], w0)), v[m]);
    uint32_t a[4];
#pragma unroll
    for (int m = 0; m < 4; m++) a[m] = (t & 1) ? v[(m + 3) & 3] : v[m];
    res[h] = (t & 2) ? make_uint4(a[2], a[3], a[0], a[1]) : make_uint4(a[0], a[1], a[2], a[3]);
  }
}

__device__ __forceinline__ void prep_gate(const Params& p, int b, int w, int lane) {
  uint2 gw[5], x[4][5];
#pragma unroll
  for (int j = 0; j < 5; j++) gw[j] = ldg64(reinterpret_cast<const uint2*>(p.gate_w) + lane + 32 * j);
#pragma unroll
  for (int i = 0; i < 4; i++)
#pragma unroll
    for (int j = 0; j < 5; j++)
      x[i][j] = ldg64(reinterpret_cast<const uint2*>(p.q) + (16 * b + 4 * w + i) * (DIM / 4) + lane + 32 * j);
  float s[4];
#pragma unroll
  for (int i = 0; i < 4; i++) {
    s[i] = 0.f;
#pragma unroll
    for (int j = 0; j < 5; j++) {
      const uint32_t m0 = bmul(x[i][j].x, gw[j].x), m1 = bmul(x[i][j].y, gw[j].y);
      s[i] += (bf_lo(m0) + bf_hi(m0)) + (bf_lo(m1) + bf_hi(m1));
    }
  }
  const bool h = lane & 16, q = lane & 8;
  const float a = (h ? s[2] : s[0]) + __shfl_xor_sync(0xffffffffu, h ? s[0] : s[2], 16);
  const float c = (h ? s[3] : s[1]) + __shfl_xor_sync(0xffffffffu, h ? s[1] : s[3], 16);
  float z = (q ? c : a) + __shfl_xor_sync(0xffffffffu, q ? a : c, 8);
#pragma unroll
  for (int o = 4; o > 0; o >>= 1) z += __shfl_xor_sync(0xffffffffu, z, o);
  z = bf_lo(pack2(z, 0.f));
  if ((lane & 7) == 0) g_gate[16 * b + 4 * w + (lane >> 3)] = bf_lo(pack2(__fdividef(1.f, 1.f + __expf(-z)), 0.f));
}

__device__ __forceinline__ uint32_t bmax(uint32_t a, uint32_t b) {
  uint32_t d;
  asm("max.bf16x2 %0, %1, %2;" : "=r"(d) : "r"(a), "r"(b));
  return d;
}
__device__ __forceinline__ void softmax_two(const float (&l)[2][2], uint32_t& p0, uint32_t& p1) {
  constexpr float kScale = 0.22360679774997896f, kLog2e = 1.4426950408889634f;
  const uint32_t r0 = pack2(l[0][0], l[1][0]), r1 = pack2(l[0][1], l[1][1]);
  const uint32_t x0 = pack2(bf_lo(r0) * kScale, bf_hi(r0) * kScale), x1 = pack2(bf_lo(r1) * kScale, bf_hi(r1) * kScale);
  uint32_t m = bmax(x0, x1);
  m = bmax(m, __shfl_xor_sync(0xffffffffu, m, 1));
  m = bmax(m, __shfl_xor_sync(0xffffffffu, m, 2));
  const float m0 = bf_lo(m) * kLog2e, m1 = bf_hi(m) * kLog2e;
  p0 = pack2(ex2(bf_lo(x0) * kLog2e - m0), ex2(bf_lo(x1) * kLog2e - m0));
  p1 = pack2(ex2(bf_hi(x0) * kLog2e - m1), ex2(bf_hi(x1) * kLog2e - m1));
}

__device__ __forceinline__ void halo_read(uint32_t (&kpv)[10], uint32_t (&vpv)[10], uint32_t (&tg)[7], const uint4* hp) {
#pragma unroll
  for (int j = 0; j < 7; j++) {
    uint32_t x0, x1, x2;
    asm volatile("ld.relaxed.gpu.global.v4.u32 {%0, %1, %2, %3}, [%4];"
                 : "=r"(x0), "=r"(x1), "=r"(x2), "=r"(tg[j]) : "l"(hp + 32 * j) : "memory");
    if (j < 4) kpv[3 * j] = x0; else vpv[3 * j - 10] = x0;
    if (j < 3) kpv[3 * j + 1] = x1; else vpv[3 * j - 9] = x1;
    if (j < 3) kpv[3 * j + 2] = x2; else if (j < 6) vpv[3 * j - 8] = x2;
  }
}

template <int ROT>
__device__ __forceinline__ void pack_qkv(const float* acc, uint32_t (&qlo)[10], uint32_t (&qhi)[10], uint32_t (&klo)[10],
                                         uint32_t (&khi)[10], uint32_t (&vlo)[10], uint32_t (&vhi)[10]) {
#pragma unroll
  for (int j = 0; j < 10; j++) {
    const int x = (j + ROT) % 10, tq = x < 8 ? x : 16 + x, tk = x < 8 ? 8 + x : 18 + x, tv = x < 8 ? 16 + x : 20 + x;
    khi[j] = pack2(acc[4 * tk + 2], acc[4 * tk + 3]);
    vhi[j] = movm(pack2(acc[4 * tv + 2], acc[4 * tv + 3]));
    qlo[j] = pack2(acc[4 * tq], acc[4 * tq + 1]);
    qhi[j] = pack2(acc[4 * tq + 2], acc[4 * tq + 3]);
    klo[j] = pack2(acc[4 * tk], acc[4 * tk + 1]);
    vlo[j] = pack2(acc[4 * tv], acc[4 * tv + 1]);
    asm volatile("" : "+r"(khi[j]), "+r"(qlo[j]), "+r"(qhi[j]), "+r"(klo[j]), "+r"(vlo[j]));
  }
}

template <int ROT> __device__ __forceinline__ void halo_send(const float* acc, uint4* ho, uint32_t tag) {
#pragma unroll
  for (int j = 0; j < 7; j++) {
    uint32_t x[3];
#pragma unroll
    for (int e = 0; e < 3; e++) {
      const int i = 3 * j + e, y = (i % 10 + ROT) % 10, tk = y < 8 ? 8 + y : 18 + y, tv = y < 8 ? 16 + y : 20 + y;
      x[e] = i < 10 ? pack2(acc[4 * tk + 2], acc[4 * tk + 3]) : i < 20 ? movm(pack2(acc[4 * tv + 2], acc[4 * tv + 3])) : 0u;
    }
    asm volatile("st.relaxed.gpu.global.v4.u32 [%0], {%1, %2, %3, %4};" ::"l"(ho + 32 * j), "r"(x[0]), "r"(x[1]), "r"(x[2]), "r"(tag) : "memory");
  }
}

__device__ __forceinline__ void attention(float* acc, uint32_t sb, int b, int par, int w, int lane, uint32_t tag) {
  const int g = lane >> 2, t = lane & 3;
  uint32_t klo[10], khi[10], vlo[10], vhi[10], qlo[10], qhi[10], kpv[10], vpv[10];
  if (HALO_FIRST && w == 3 && b < NCTA - 8) {
    uint4* ho = g_halo + (b * 2 + par) * 224 + lane;
    if (tail_first(b & 7)) halo_send<8>(acc, ho, tag);
    else halo_send<0>(acc, ho, tag);
    TSIF(par == 0, 76);
    pin<120>(acc);
  }
  if (tail_first(b & 7)) pack_qkv<8>(acc, qlo, qhi, klo, khi, vlo, vhi);
  else pack_qkv<0>(acc, qlo, qhi, klo, khi, vlo, vhi);
  const uint32_t xa = sb + OFF_KVX + (par * 3) * 2560 + lane * 16;
  if (w < 3) {
    sts128(xa + w * 2560, khi[0], khi[1], khi[2], khi[3]);
    sts128(xa + w * 2560 + 512, khi[4], khi[5], khi[6], khi[7]);
    sts128(xa + w * 2560 + 1024, khi[8], khi[9], vhi[0], vhi[1]);
    sts128(xa + w * 2560 + 1536, vhi[2], vhi[3], vhi[4], vhi[5]);
    sts128(xa + w * 2560 + 2048, vhi[6], vhi[7], vhi[8], vhi[9]);
  } else if (!HALO_FIRST && b < NCTA - 8) {
    uint4* ho = g_halo + (b * 2 + par) * 224 + lane;
#pragma unroll
    for (int j = 0; j < 7; j++) {
      const uint32_t x0 = j < 4 ? khi[3 * j] : vhi[3 * j - 10], x1 = j < 3 ? khi[3 * j + 1] : vhi[3 * j - 9];
      const uint32_t x2 = j < 3 ? khi[3 * j + 2] : j < 6 ? vhi[3 * j - 8] : 0u;
      asm volatile("st.relaxed.gpu.global.v4.u32 [%0], {%1, %2, %3, %4};" ::"l"(ho + 32 * j), "r"(x0), "r"(x1), "r"(x2), "r"(tag) : "memory");
    }
  }
  TSIF(par == 0 && w == 1, 64);
  TSIF(par == 0 && w == 3 && !HALO_FIRST, 76);
#pragma unroll
  for (int j = 0; j < 10; j++) vlo[j] = movm(vlo[j]);
  const bool far0 = 2 * t > g, far1 = 2 * t + 1 > g;
  const uint32_t mfar = (far0 ? 0x0000FFFFu : 0u) | (far1 ? 0xFFFF0000u : 0u);
  float slo[4][2], shi[4][2], lg[2][2];
  uint32_t phi[4], plo[4], qml[4], qmh[4];
#pragma unroll
  for (int h = 0; h < 4; h++) {
    const int f = h == 0 ? 0 : h == 1 ? 3 : h == 2 ? 5 : 8, hf = h < 2 ? 2 : 7;
    const bool mine = (h & 1) ? t >= 2 : t < 2;
    qml[h] = mine ? qlo[hf] : 0u;
    qmh[h] = mine ? qhi[hf] : 0u;
    float a[4] = {0.f, 0.f, 0.f, 0.f}, c[4] = {0.f, 0.f, 0.f, 0.f};
    mma16816(a, qlo[f], qhi[f], qlo[f + 1], qhi[f + 1], klo[f], klo[f + 1]);
    mma16816(c, qlo[f], qhi[f], qlo[f + 1], qhi[f + 1], khi[f], khi[f + 1]);
    mma1688(a, qml[h], qmh[h], klo[hf]);
    mma1688(c, qml[h], qmh[h], khi[hf]);
    slo[h][0] = a[0];
    slo[h][1] = a[1];
    shi[h][0] = lg[h & 1][0] = far0 ? a[2] : c[2];
    shi[h][1] = lg[h & 1][1] = far1 ? a[3] : c[3];
    if (!ATT_MERGE && (h & 1)) softmax_two(lg, phi[h - 1], phi[h]);
  }
  TSIF(par == 0 && w == 1, 65);
  wg_sync(1 + par);
  TSIF(par == 0 && w == 1, 66);
  const bool nohist = (w == 0) && (b < 8);
  const uint4* hp = g_halo + ((b - 8) * 2 + par) * 224 + lane;
  uint32_t tg[7];
  if (w > 0) {
    const uint4 v0 = lds128(xa + (w - 1) * 2560), v1 = lds128(xa + (w - 1) * 2560 + 512), v2 = lds128(xa + (w - 1) * 2560 + 1024);
    const uint4 v3 = lds128(xa + (w - 1) * 2560 + 1536), v4 = lds128(xa + (w - 1) * 2560 + 2048);
    kpv[0] = v0.x; kpv[1] = v0.y; kpv[2] = v0.z; kpv[3] = v0.w; kpv[4] = v1.x; kpv[5] = v1.y; kpv[6] = v1.z; kpv[7] = v1.w;
    kpv[8] = v2.x; kpv[9] = v2.y; vpv[0] = v2.z; vpv[1] = v2.w; vpv[2] = v3.x; vpv[3] = v3.y; vpv[4] = v3.z; vpv[5] = v3.w;
    vpv[6] = v4.x; vpv[7] = v4.y; vpv[8] = v4.z; vpv[9] = v4.w;
  } else if (nohist) {
#pragma unroll
    for (int j = 0; j < 10; j++) kpv[j] = vpv[j] = 0u;
  } else {
    TSIF(par == 0, 77);
    halo_read(kpv, vpv, tg, hp);
  }
  if (w == 0 && !nohist) {
    int spins = 0;
    while (true) {
      bool ok = true;
#pragma unroll
      for (int j = 0; j < 7; j++) ok = ok && tg[j] == tag;
      if (__all_sync(0xffffffffu, ok) || ++spins > SPIN_LIMIT) break;
      halo_read(kpv, vpv, tg, hp);
    }
    TSIF(par == 0, 79);
  }
#pragma unroll
  for (int h = 0; h < 4; h++) {
    const int f = h == 0 ? 0 : h == 1 ? 3 : h == 2 ? 5 : 8, hf = h < 2 ? 2 : 7;
    float a[4] = {0.f, 0.f, 0.f, 0.f};
    mma16816(a, qlo[f], qhi[f], qlo[f + 1], qhi[f + 1], kpv[f], kpv[f + 1]);
    mma1688(a, qml[h], qmh[h], kpv[hf]);
    const float ninf = __int_as_float(0xff800000);
    lg[h & 1][0] = far0 ? (nohist ? ninf : a[0]) : slo[h][0];
    lg[h & 1][1] = far1 ? (nohist ? ninf : a[1]) : slo[h][1];
    if (h & 1) {
      softmax_two(lg, plo[h - 1], plo[h]);
      if (ATT_MERGE) {
        const float lh[2][2] = {{shi[h - 1][0], shi[h - 1][1]}, {shi[h][0], shi[h][1]}};
        softmax_two(lh, phi[h - 1], phi[h]);
      }
    }
  }
  TSIF(par == 0 && w <= 1, 67 + w);
  uint32_t ov[20];
#pragma unroll
  for (int hp = 0; hp < 2; hp++) {
    const int hf = hp ? 7 : 2;
    float sh[4] = {0.f, 0.f, 0.f, 0.f}, i0 = 0.f, i1 = 0.f;
#pragma unroll
    for (int e = 0; e < 2; e++) {
      const int h = 2 * hp + e, f = h == 0 ? 0 : h == 1 ? 3 : h == 2 ? 5 : 8;
      const uint32_t a0 = plo[h] & mfar, a2 = plo[h] & ~mfar, a3 = phi[h] & mfar, c1 = phi[h] & ~mfar;
      float sum[4] = {0.f, 0.f, 0.f, 0.f};
      mma1688(sum, plo[h], phi[h], 0x3F803F80u);
      const float r0 = rcp(sum[0]), r1 = rcp(sum[2]);
#pragma unroll
      for (int j = f; j < f + 2; j++) {
        float o[4] = {0.f, 0.f, 0.f, 0.f};
        mma16816(o, a0, 0u, a2, a3, vpv[j], vlo[j]);
        mma1688(o, 0u, c1, vhi[j]);
        ov[2 * j] = pack2(o[0] * r0, o[1] * r0);
        ov[2 * j + 1] = pack2(o[2] * r1, o[3] * r1);
      }
      const bool mine = e ? g >= 4 : g < 4;
      mma16816(sh, a0, 0u, a2, a3, mine ? vpv[hf] : 0u, mine ? vlo[hf] : 0u);
      mma1688(sh, 0u, c1, mine ? vhi[hf] : 0u);
      if (e == 0 || t >= 2) {
        i0 = r0;
        i1 = r1;
      }
    }
    ov[2 * hf] = pack2(sh[0] * i0, sh[1] * i0);
    ov[2 * hf + 1] = pack2(sh[2] * i1, sh[3] * i1);
  }
  TS(32 + 4 * par + w);
  mbar_wait(sb + OFF_BAR + 8 * B_P1, 0);
  const uint32_t oa = sb + OFF_OA + (lane >> 4) * 2048 + (32 * w + 2 * (lane & 15) + par) * 16;
#pragma unroll
  for (int j = 0; j < 5; j++) stsm4(oa + 4096 * j, ov + 4 * j);
  TSIF(par == 0 && w == 0, 120);
  fence_async_smem();
  TSIF(par == 0 && w == 0, 121);
  __syncwarp();
  if (lane == 0) mbar_arrive(sb + OFF_BAR + 8 * B_ATTN);
  TSM(w == 0 || w == 2, 122 + par + (w == 2 ? 3 : 0));
}

struct Maps {
  CUtensorMap x, wm, wt, k, v, y, wo, qm, qt, om, ot, u;
};

__device__ __forceinline__ void load_stage(uint32_t sb, int kb, int b, const Maps& m) {
  const uint32_t st = sb + (kb & 3) * STAGE_BYTES, bar = sb + OFF_BAR + 8 * (B_FULL1 + (kb & 3));
  const int r = b >> 3, hg = b & 7, slab = kb - KV_KB;
  const bool kv = slab >= 0 && slab < 5;
  const uint32_t kbar = sb + OFF_BAR + 8 * (B_KV + slab), dst = sb + OFF_KVS + slab * KVS_BYTES;
  mbar_expect_tx(bar, STAGE_BYTES);
  if (kv) mbar_expect_tx(kbar, KVS_BYTES);
  tma_3d(st, &m.x, 64 * kb, 64 * r, 0, bar);
  if (kv && KV_MIX) tma_3d(dst, &m.k, 0, 32 * (b >> 1) - 3, 2 * slab + (b & 1), kbar);
  tma_3d(st + ST_W, &m.wm, 80 * hg + (tail_first(hg) ? 16 : 0), 64 * kb, 0, bar);
  if (kv && KV_MIX) tma_3d(dst + KVS_V, &m.v, 0, 32 * (b >> 1), 2 * slab + (b & 1), kbar);
  tma_3d(st + ST_WT, &m.wt, 80 * hg + (tail_first(hg) ? 0 : 64), 64 * kb, 0, bar);
  if (kv && !KV_MIX) tma_3d(dst, &m.k, 0, 32 * (b >> 1) - 3, 2 * slab + (b & 1), kbar);
  if (kv && !KV_MIX) tma_3d(dst + KVS_V, &m.v, 0, 32 * (b >> 1), 2 * slab + (b & 1), kbar);
}

__global__ void __launch_bounds__(NTHR, 1) fused_kernel(const __grid_constant__ Maps m, const Params p) {
  extern __shared__ __align__(1024) uint8_t smem[];
  const uint32_t sb = (uint32_t)__cvta_generic_to_shared(smem);
  const uint32_t bars = sb + OFF_BAR;
  const int tid = threadIdx.x, lane = tid & 31;
  int b = blockIdx.x;
  if (BMAP == 1) b = (((b & 63) >> 3) * 2 + (b & 1)) * 8 + (((b < 64 ? 0x6521 : 0x7430) >> (4 * ((b >> 1) & 3))) & 7);
  if (BMAP == 2) b = ((b & 63) >> 2) * 8 + (((b < 64 ? 0x6521 : 0x7430) >> (4 * (b & 3))) & 7);
  if (BMAP == 3) b = (((b & 63) >> 3) * 2 + (b & 1)) * 8 + (((b < 64 ? 0x7430 : 0x6521) >> (4 * ((b >> 1) & 3))) & 7);
  if (BMAP == 4) b = (((b >> 4) * 2 + (b & 1)) * 8) + ((b >> 1) & 7);
  if (BMAP == 5) b = 127 - b;
  const int r = b >> 3, hg = b & 7;

  if (tid == T_ISSUE) {
    TSM(true, 0);
#pragma unroll
    for (int i = 0; i < 4; i++) mbar_init(bars + 8 * (B_FULL1 + i), 1);
#pragma unroll
    for (int i = 0; i < 3; i++) mbar_init(bars + 8 * (B_KV + i), 1);
    fence_async_smem();
#pragma unroll 1
    for (int kb = 0; kb <= PRE2; kb++) load_stage(sb, kb, b, m);
  } else if (tid >= T_PF && tid < T_PF + 12) {
    tm_prefetch(&m.x + (tid - T_PF));
  } else if (tid == T_INIT) {
#pragma unroll
    for (int i = 0; i < 4; i++) mbar_init(bars + 8 * (B_EMPTY1 + i), 8);
#pragma unroll
    for (int i = 0; i < 8; i++) mbar_init(bars + 8 * (B_FULL2 + i), 1);
#pragma unroll
    for (int i = 0; i < 4; i++) mbar_init(bars + 8 * (B_EMPTY2 + i), 8);
#pragma unroll
    for (int i = 0; i < 4; i++) mbar_init(bars + 8 * (B_U + i), 1);
    mbar_init(bars + 8 * B_HA, 4);
    mbar_init(bars + 8 * B_GATE, 4);
    mbar_init(bars + 8 * B_HB, 1);
    mbar_init(bars + 8 * B_KVD, 4);
    mbar_init(bars + 8 * B_QF, 1);
    mbar_init(bars + 8 * B_ATTN, 8);
    mbar_init(bars + 8 * B_P1, 8);
    mbar_init(bars + 8 * B_C34, 1);
#pragma unroll
    for (int i = 0; i < 5; i++) mbar_init(bars + 8 * (B_YST + i), 4);
#pragma unroll
    for (int i = 0; i < 5; i++) mbar_init(bars + 8 * (B_US + i), 4);
    mbar_init(bars + 8 * B_YSIG, 1);
    mbar_init(bars + 8 * B_YFULL, 1);
    mbar_init(bars + 8 * B_EPOCH, 1);
    mbar_init(bars + 8 * B_PREP, 4);
    mbar_init(bars + 8 * B_USIG, 1);
    mbar_init(bars + 8 * B_WST, 1);
#pragma unroll
    for (int i = 3; i < 5; i++) mbar_init(bars + 8 * (B_KV + i), 1);
    mbar_init(bars + 8 * B_E3, 8);
    mbar_init(bars + 8 * B_LAST, 1);
    mbar_init(bars + 8 * B_OSIG, 1);
    mbar_init(bars + 8 * B_WOP, 1);
    fence_async_smem();
  }
  const int warp = __shfl_sync(0xffffffffu, tid >> 5, 0), wg = warp >> 2, w = warp & 3;
  __syncthreads();

  if (wg == 3) {
    asm volatile("setmaxnreg.dec.sync.aligned.u32 56;");
    if (w == 0) {
      if (lane == 0) {
#pragma unroll 1
        for (int kb = 1 + PRE2; kb < 10; kb++) {
          if (kb >= 4) mbar_wait(bars + 8 * (kb == 7 ? B_E3 : B_EMPTY1 + (kb & 3)), (kb >> 3) & 1);
          TSIF(kb >= 4, 44 + kb);
          load_stage(sb, kb, b, m);
          TSIF(kb == 3, 60);
          if (kb == TRIG_KB) mbar_arrive(bars + 8 * B_LAST);
        }
        mbar_wait(bars + 8 * B_WOP, 0);
        mbar_wait(bars + 8 * WL_TRIG, 0);
        mbar_wait(bars + 8 * B_EPOCH, 0);
        flag_wait(g_cnt + C_W + 32 * hg, (lds32(sb + OFF_EPOCH) + 1) * 16);
        TS(30);
#pragma unroll 1
        for (int j = 0; j < 8; j++) {
          if (j >= 6) mbar_wait(bars + 8 * (B_EMPTY2 + j - 6), 0);
          if (j == 4) mbar_wait(bars + 8 * B_ATTN, 0);
          TSIF(j >= 6, 100 + j);
          if (RF_GATE && j == 6) mbar_wait(bars + 8 * B_YSIG, 0);
          mbar_expect_tx(bars + 8 * (B_FULL2 + j), j == 0 ? WO_BYTES : j == 5 ? O_BYTES + WO_BYTES + 512 : O_BYTES + WO_BYTES);
          bulk_load(sb + off_w(j), g_WO + (hg * 8 + step_src(hg, j)) * 800, WO_BYTES, bars + 8 * (B_FULL2 + j));
        }
        mbar_wait(bars + 8 * (B_EMPTY2 + 3), 0);
        mbar_expect_tx(bars + 8 * B_QF, O_BYTES);
        tma_2d(sb + OFF_QS, &m.qm, 80 * hg, 128 * r, bars + 8 * B_QF);
        tma_2d(sb + OFF_QT, &m.qt, 80 * hg + 64, 128 * r, bars + 8 * B_QF);
      }
    } else if (w == 1) {
      unsigned epoch = 0;
      if (lane == 0) {
        epoch = atomicAdd(g_cnt + C_LAUNCH, 1u) / NCTA;
        asm volatile("st.shared.u32 [%0], %1;" ::"r"(sb + OFF_EPOCH), "r"(epoch) : "memory");
        mbar_arrive(bars + 8 * B_EPOCH);
        mbar_wait(bars + 8 * B_KVD, 0);
        mbar_expect_tx(bars + 8 * B_HB, 5 * 4096);
#pragma unroll 1
        for (int c = 0; c < 5; c++) {
          if (c == 3) mbar_wait(bars + 8 * B_S3, 0);
          bulk_load(sb + off_ch(c) + U_BYTES, p.ssm_k + (5 * b + c) * SEQ, 4096, bars + 8 * B_HB);
        }
#pragma unroll
        for (int c = 0; c < 4; c++) mbar_expect_tx(bars + 8 * (B_U + c), c < 3 ? U_BYTES : 2 * U_BYTES);
        const uint4* usrc = g_U + 5 * b * U_PITCH;
        mbar_wait(bars + 8 * B_USIG, 0);
        flag_wait(g_cnt + C_PREP + 32 * (b & 15), (epoch + 1) * NCTA);
        TS(23);
#pragma unroll
        for (int c = 0; c < 5; c++) {
          if (c == 3) mbar_wait(bars + 8 * (B_U + 2), 0);
          bulk_load(sb + off_ch(c), usrc + c * U_PITCH, U_BYTES, bars + 8 * (B_U + (c < 3 ? c : 3)));
          TSIF(c == 0 || c == 4, 116 + (c >> 2));
        }
      }
      epoch = __shfl_sync(0xffffffffu, epoch, 0);
      if (lane < 8) {
        const int src = (b & ~7) | step_src(hg, lane);
        mbar_wait(bars + 8 * B_OSIG, 0);
        TS(20);
        flag_wait(g_cnt + C_O + 32 * src, epoch + 1);
        if (lane >= 1 && lane < 4) bulk_load(sb + off_o(lane), g_O + src * 1280, O_BYTES, bars + 8 * (B_FULL2 + lane));
        __syncwarp(0xff);
        TS(21);
        if (lane == 5) bulk_load(sb + OFF_GATE, g_gate + 128 * r, 512, bars + 8 * (B_FULL2 + 5));
#pragma unroll 1
        for (int j = 4; j < 8; j++) {
          if (lane == j) {
            mbar_wait(bars + 8 * (j < 6 ? B_C34 : B_EMPTY2 + j - 6), 0);
            if (RF_GATE && j == 6) mbar_wait(bars + 8 * B_YSIG, 0);
            bulk_load(sb + off_o(j), g_O + src * 1280, O_BYTES, bars + 8 * (B_FULL2 + j));
          }
          __syncwarp(0xff);
        }
        TS(22);
      }
    } else if (w == 2) {
      mbar_wait(bars + 8 * B_PREP, 0);
      flag_signal(g_cnt + C_PREP, 16, lane);
      TS(25);
      if (lane == 0) mbar_arrive(bars + 8 * B_USIG);
      mbar_wait(bars + 8 * B_GATE, 0);
      if ((NOMB & 1) && lane == 0) asm volatile("fence.release.gpu;" ::: "memory");
      mbar_wait(bars + 8 * B_ATTN, 0);
      if (lane == 0) {
        if (O_DEFER) mbar_wait(bars + 8 * (B_U + 3), 0);
        asm volatile("cp.async.bulk.global.shared::cta.bulk_group [%0], [%1], 20480;\ncp.async.bulk.commit_group;\n"
                     "cp.async.bulk.wait_group 0;\nfence.proxy.async.global;" ::"l"(g_O + b * 1280), "r"(sb + OFF_OA) : "memory");
      }
      TS(74);
      if (!(NOMB & 1)) flag_signal(g_cnt + C_O + 32 * b, 1, lane);
      else if (lane == 0) flag_bump(g_cnt + C_O + 32 * b);
      TS(26);
      if (lane == 0) mbar_arrive(bars + 8 * B_OSIG);

    } else {
      if (lane == 0) {
        uint4* dst = g_WO + (hg * 8 + (r >> 1)) * 800 + (r & 1) * 80;
        mbar_wait(bars + 8 * B_P1, 0);
        mbar_wait(bars + 8 * WB_TRIG, 0);
        mbar_expect_tx(bars + 8 * B_WST, WO_BYTES / 2);
        tma_3d(sb + OFF_WS, &m.wo, 0, 40 * r, 5 * hg, bars + 8 * B_WST);
        mbar_wait(bars + 8 * B_WST, 0);
        mbar_wait(bars + 8 * WO_TRIG, 0);
#pragma unroll 1
        for (int n = 0; n < 5; n++)
          asm volatile("cp.async.bulk.global.shared::cta.bulk_group [%0], [%1], 1280;" ::"l"(dst + 160 * n), "r"(sb + OFF_WS + 1280 * n) : "memory");
        asm volatile("cp.async.bulk.commit_group;\ncp.async.bulk.wait_group 0;\nfence.proxy.async.global;" ::: "memory");
        if (!(NOMB & 4)) asm volatile("fence.release.gpu;" ::: "memory");
        flag_bump(g_cnt + C_W + 32 * hg);
        mbar_arrive(bars + 8 * B_WOP);
        TS(71);
#pragma unroll 1
        for (int c = 0; c < 5; c++) {
          mbar_wait(bars + 8 * (B_YST + c), 0);
          asm volatile("cp.async.bulk.global.shared::cta.bulk_group [%0], [%1], 4096;\ncp.async.bulk.commit_group;"
                       ::"l"(g_Y + (5 * b + c) * Y_PITCH), "r"(sb + off_ch(c)) : "memory");
          if (c == 2) {
            asm volatile("cp.async.bulk.wait_group.read 0;" ::: "memory");
            mbar_arrive(bars + 8 * B_C34);
          }
        }
        asm volatile("cp.async.bulk.wait_group 0;\nfence.proxy.async.global;" ::: "memory");
        TS(75);
        if (!(NOMB & 2)) asm volatile("fence.release.gpu;" ::: "memory");
        flag_bump(g_cnt + C_Y + 32 * (b >> 4));
        TS(27);
        mbar_arrive(bars + 8 * B_YSIG);
        mbar_expect_tx(bars + 8 * B_YFULL, 20480);
        flag_wait(g_cnt + C_Y + 32 * hg, (lds32(sb + OFF_EPOCH) + 1) * 16);
        TS(24);
        tma_2d(sb + OFF_YT, &m.y, 128 * r, 80 * hg, bars + 8 * B_YFULL);
        tma_2d(sb + OFF_YT + 10240, &m.y, 128 * r + 64, 80 * hg, bars + 8 * B_YFULL);
      }
    }
  } else {
    asm volatile("setmaxnreg.inc.sync.aligned.u32 152;");
    if (wg < 2) {
      float acc[120];
#pragma unroll
      for (int i = 0; i < 120; i++) acc[i] = 0.f;
      const uint32_t da = desc_lo(sb + wg * 8192, 16), db = desc_lo(sb + ST_W, 8192), dc = desc_lo(sb + ST_WT, 2048);
      if (PW1) pin<120>(acc);
      if (PW1 == 2) mbar_wait(bars + 8 * B_FULL1, 0);
#pragma unroll 1
      for (int kb = 0; kb < 10; kb++) {
        mbar_wait(bars + 8 * (B_FULL1 + (kb & 3)), (kb >> 2) & 1);
        const uint32_t so = (kb & 3) * (STAGE_BYTES >> 4);
        wg_fence();
#pragma unroll
        for (int k = 0; k < 4; k++) {
          WgSST<192>::mma<HI_SW128, HI_SW128>(acc, da + so + 2 * k, db + so + 128 * k, 1);
          WgSST<48>::mma<HI_SW128, HI_SW32>(acc + 96, da + so + 2 * k, dc + so + 32 * k, 1);
        }
        wg_commit();
        wg_wait<1>();
        if (kb > 0 && lane == 0) mbar_arrive(bars + 8 * (kb == 4 ? B_E3 : B_EMPTY1 + ((kb - 1) & 3)));
      }
      mbar_wait(bars + 8 * B_EPOCH, 0);
      const uint32_t tag = lds32(sb + OFF_EPOCH) + 1;
      mbar_wait(bars + 8 * B_S3, 0);
      wg_wait<0>();
      pin<120>(acc);
      if (lane == 0) mbar_arrive(bars + 8 * B_P1);
      TSM(w == 0, 3 + wg);
      attention(acc, sb, b, wg, w, lane, tag);
    } else {
      const int tw = tid & 127, chl = 64 * (b & 1) + 8 * w + (lane >> 2);
      uint4* up = g_U + chl * U_PITCH + ((4 * (b >> 1) + (lane & 3)) ^ ((b >> 2) & 1));
      uint2 sw[10];
      uint32_t dv = 0;
      if (lane < 5) dv = __ldg(reinterpret_cast<const unsigned short*>(p.ssm_D) + 5 * b + lane);
#pragma unroll
      for (int i = 0; i < 10; i++) sw[i] = ldg64(reinterpret_cast<const uint2*>(p.shift_k) + chl + 128 * (i >> 1) + 32 * (i & 1));
      uint32_t tab[12];
      uint32_t tt[2];
      fft_tables(tab, tw);
      fft_twiddles(tt, tw);
      uint4 res[10];
#pragma unroll
      for (int i = 0; i < 10; i++) res[i] = make_uint4(0, 0, 0, 0);
#pragma unroll 1
      for (int slab = 0; slab < 5; slab++) {
#pragma unroll
        for (int i = 0; i < 8; i++) res[i] = res[i + 2];
        prep_slab(res + 8, sw, sb, slab, w, lane);
        TSIF(w == 0, 99 + 4 * slab);
#pragma unroll
        for (int i = 0; i < 8; i++) sw[i] = sw[i + 2];
      }
      TSIF(w == 0, 28);
      __syncwarp();
      if (lane == 0) mbar_arrive(bars + 8 * B_KVD + ((res[8].x ^ res[9].x) & p.zero));
      mbar_wait(bars + 8 * B_KVD, 0);
      fft_tables_store(tab, sb, tw);
      mbar_wait(bars + 8 * B_LAST, 0);
#pragma unroll
      for (int i = 0; i < 10; i++) up[(128 * (i >> 1) + 32 * (i & 1)) * U_PITCH] = res[i];
      __syncwarp();
      if (lane == 0) mbar_arrive(bars + 8 * B_PREP);
      TSIF(w == 0 && !U_TMA, 5);
      mbar_wait(bars + 8 * (G_AFTER ? B_USIG : B_LAST), 0);
      prep_gate(p, b, w, lane);
      __syncwarp();
      if (lane == 0) mbar_arrive(bars + 8 * B_GATE);
      TSIF(w == 0, 72);
      mbar_wait(bars + 8 * B_HB, 0);
      TSIF(w == 0, 2);
      const uint32_t ha = sb + U_BYTES + ((tw >> 3) * 16 + 8 + (tw & 7)) * 16;
      uint4 hv[5];
#pragma unroll
      for (int c = 0; c < 5; c++) hv[c] = lds128(ha + off_ch(c));
      __syncwarp();
#pragma unroll
      for (int c = 0; c < 5; c++) sts128((ha ^ 16) + off_ch(c), hv[c].x, hv[c].y, hv[c].z, hv[c].w);
      asm volatile("st.shared.v2.u32 [%0], {%1, %2};" ::"r"(sb + OFF_TT + 8 * tw), "r"(tt[0]), "r"(tt[1]) : "memory");
      if (tw < 5) asm volatile("st.shared.f32 [%0], %1;" ::"r"(sb + OFF_D + 4 * tw), "f"(bf_lo(dv) * 0.125f) : "memory");
      fence_async_smem();
      __syncwarp();
      if (lane == 0) mbar_arrive(bars + 8 * B_HA);
      TSIF(w == 0, 6);
    }

    FftConst fc;
    TSM(w == 0 && wg == 0, 104);
    mbar_wait(bars + 8 * B_HA, 0);
    fft_matrices(fc, sb, w, lane);
    TSM(w == 0 && wg == 0, 105);
    if (ATT_GATE && !H_EARLY) mbar_wait(bars + 8 * B_ATTN, 0);
    TSM(w == 0 && wg == 2, 124);
#pragma unroll 1
    for (uint32_t tasks = wg == 0 ? TASK0 : wg == 1 ? TASK1 : TASK2; tasks; tasks >>= 4) {
      const int c = (tasks & 7) - 1;
      conv_channel(fc, sb, c, wg, w, lane);
      if (lane == 0) mbar_arrive(bars + 8 * (B_YST + c));
      TSM(w == 0, 10 + c);
    }

    if (wg < 2) {
      const int g = lane >> 2;
      float acc[40];
#pragma unroll
      for (int i = 0; i < 40; i++) acc[i] = 0.f;
      const uint32_t da = desc_lo(sb + wg * 1024, 2048), db = desc_lo(sb, 2560);
      mbar_wait(bars + 8 * B_ATTN, 0);
      mbar_wait(bars + 8 * (B_YST + 3), 0);
      mbar_wait(bars + 8 * (B_YST + 4), 0);
      if (PW2) mbar_wait(bars + 8 * B_FULL2, 0);
      TSM(w == 0, 15 + wg);
#pragma unroll 1
      for (int j = 0; j < 8; j++) {
        mbar_wait(bars + 8 * (B_FULL2 + j), 0);
        const uint32_t oa = da + (off_o(j) >> 4), ob = db + (off_w(j) >> 4);
        wg_fence();
#pragma unroll
        for (int k = 0; k < 5; k++) WgSST<80>::mma<HI_NONE, HI_SW32>(acc, oa + 256 * k, ob + 32 * k, 1);
        wg_commit();
        wg_wait<1>();
        if (j >= 1 && j <= 4 && lane == 0) mbar_arrive(bars + 8 * (B_EMPTY2 + j - 1));
      }
      TSIF(w == 0 && wg == 0, 113);
      const int tr = 64 * wg + 16 * w + (lane & 15);
      const uint32_t fm = sb + OFF_QS + tr * 128, fx = (lane >> 4) ^ (tr & 7);
      const uint32_t ft = sb + OFF_QT + tr * 32 + (((lane >> 4) ^ (tr >> 2)) & 1) * 16;
      const float g0 = __uint_as_float(lds32(sb + OFF_GATE + (64 * wg + 16 * w + g) * 4));
      const float g1 = __uint_as_float(lds32(sb + OFF_GATE + (64 * wg + 16 * w + 8 + g) * 4));
      const uint32_t ga = pack2(g0, g0), gb = pack2(g1, g1);
      const uint32_t na = pack2(1.f - g0, 1.f - g0), nb = pack2(1.f - g1, 1.f - g1);

      wg_wait<0>();
      pin<40>(acc);
      TSM(w == 0, 17 + wg);
      uint32_t pb[20];
#pragma unroll
      for (int j = 0; j < 10; j++) {
        pb[2 * j] = bmul(na, pack2(acc[4 * j], acc[4 * j + 1]));
        pb[2 * j + 1] = bmul(nb, pack2(acc[4 * j + 2], acc[4 * j + 3]));
        asm volatile("" : "+r"(pb[2 * j]), "+r"(pb[2 * j + 1]));
      }
      const uint32_t ya = sb + OFF_YT + wg * 10240 + ((lane >> 4) * 8 + (lane & 7)) * 128 +
                          (((2 * w + (((lane >> 3) & 1) ^ wg)) ^ (lane & 7)) << 4);
      uint32_t qf[20];
      mbar_wait(bars + 8 * B_QF, 0);
#pragma unroll
      for (int j = 0; j < 5; j++) ldsm4(qf + 4 * j, j < 4 ? fm + ((fx ^ (2 * j)) << 4) : ft);
      mbar_wait(bars + 8 * B_YFULL, 0);
      TSM(w == 0 && wg == 0, 19);
#pragma unroll
      for (int j = 0; j < 5; j++) {
        uint32_t y[4];
        ldsm4t(y, ya + 2048 * j);
#pragma unroll
        for (int i = 0; i < 4; i++) qf[4 * j + i] = badd(bmul((i & 1) ? gb : ga, bmul(qf[4 * j + i], y[i])), pb[4 * j + i]);
      }
#pragma unroll
      for (int j = 0; j < 5; j++) stsm4(j < 4 ? fm + ((fx ^ (2 * j)) << 4) : ft, qf + 4 * j);
      fence_async_smem();
      __syncwarp();
      if (lane == 0) {
        const int row = 64 * wg + 16 * w;
        asm volatile("cp.async.bulk.tensor.2d.global.shared::cta.bulk_group [%0, {%2, %3}], [%1];"
                     ::"l"(&m.om), "r"(sb + OFF_QS + row * 128), "r"(80 * hg), "r"(128 * r + row) : "memory");
        asm volatile("cp.async.bulk.tensor.2d.global.shared::cta.bulk_group [%0, {%2, %3}], [%1];"
                     ::"l"(&m.ot), "r"(sb + OFF_QT + row * 32), "r"(80 * hg + 64), "r"(128 * r + row) : "memory");
        asm volatile("cp.async.bulk.commit_group;\ncp.async.bulk.wait_group.read 0;" ::: "memory");
      }
      TSM(true, 40 + 4 * wg + w);
      if (ENDBAR) asm volatile("bar.sync 15, 256;" ::: "memory");
    }
  }
}

typedef CUresult (*EncodeFn)(CUtensorMap*, CUtensorMapDataType, cuuint32_t, void*, const cuuint64_t*, const cuuint64_t*,
                             const cuuint32_t*, const cuuint32_t*, CUtensorMapInterleave, CUtensorMapSwizzle,
                             CUtensorMapL2promotion, CUtensorMapFloatOOBfill);

void encode(EncodeFn fn, CUtensorMap* tm, const void* base, int rank, const cuuint64_t* dims, const cuuint64_t* strides,
            const cuuint32_t* box, CUtensorMapSwizzle swz) {
  const cuuint32_t ones[3] = {1, 1, 1};
  fn(tm, CU_TENSOR_MAP_DATA_TYPE_BFLOAT16, rank, const_cast<void*>(base), dims, strides, box, ones,
     CU_TENSOR_MAP_INTERLEAVE_NONE, swz, CU_TENSOR_MAP_L2_PROMOTION_L2_128B, CU_TENSOR_MAP_FLOAT_OOB_FILL_NONE);
}

}

extern "C" void kernel_launch(void* const* d_in, const int* in_sizes, int n_in, void* d_out, int out_size) {
  (void)in_sizes; (void)n_in; (void)out_size;
  Params p;
  p.q = (const __nv_bfloat16*)d_in[0];
  p.k = (const __nv_bfloat16*)d_in[1];
  p.v = (const __nv_bfloat16*)d_in[2];
  p.shift_k = (const __nv_bfloat16*)d_in[3];
  p.ssm_k = (const __nv_bfloat16*)d_in[4];
  p.ssm_D = (const __nv_bfloat16*)d_in[5];
  p.wqkv = (const __nv_bfloat16*)d_in[7];
  p.wo = (const __nv_bfloat16*)d_in[8];
  p.gate_w = (const __nv_bfloat16*)d_in[9];
  p.out = (__nv_bfloat16*)d_out;
  p.zero = 0;

  static EncodeFn fn = nullptr;
  static void *yaddr = nullptr, *uaddr = nullptr;
  if (!fn) {
    cudaDriverEntryPointQueryResult qr;
    void* f = nullptr;
    cudaGetDriverEntryPoint("cuTensorMapEncodeTiled", &f, cudaEnableDefault, &qr);
    fn = (EncodeFn)f;
    cudaGetSymbolAddress(&yaddr, g_Y);
    cudaGetSymbolAddress(&uaddr, g_U);
    cudaFuncSetAttribute(fused_kernel, cudaFuncAttributeMaxDynamicSharedMemorySize, SMEM_BYTES);
  }
  Maps m;
  {
    const cuuint64_t dims[3] = {640, 1024, 2}, st[2] = {2560, 1280};
    const cuuint32_t box[3] = {64, 64, 2};
    encode(fn, &m.x, p.q, 3, dims, st, box, CU_TENSOR_MAP_SWIZZLE_128B);
  }
  {
    const cuuint64_t dims[3] = {640, 640, 3}, st[2] = {3840, 1280};
    const cuuint32_t box[3] = {64, 64, 3}, boxt[3] = {16, 64, 3};
    encode(fn, &m.wm, p.wqkv, 3, dims, st, box, CU_TENSOR_MAP_SWIZZLE_128B);
    encode(fn, &m.wt, p.wqkv, 3, dims, st, boxt, CU_TENSOR_MAP_SWIZZLE_32B);
  }
  {
    const cuuint64_t dims[3] = {64, 2048, 10}, st[2] = {1280, 128};
    const cuuint32_t boxk[3] = {64, 35, 1}, boxv[3] = {64, 32, 1};
    encode(fn, &m.k, p.k, 3, dims, st, boxk, CU_TENSOR_MAP_SWIZZLE_128B);
    encode(fn, &m.v, p.v, 3, dims, st, boxv, CU_TENSOR_MAP_SWIZZLE_128B);
  }
  {
    const cuuint64_t dims[3] = {16, 640, 40}, st[2] = {1280, 32};
    const cuuint32_t box[3] = {16, 40, 5};
    encode(fn, &m.wo, p.wo, 3, dims, st, box, CU_TENSOR_MAP_SWIZZLE_32B);
  }
  {
    const cuuint64_t dims[2] = {2048, 640}, st[1] = {Y_PITCH * 16};
    const cuuint32_t box[2] = {64, 80};
    encode(fn, &m.y, yaddr, 2, dims, st, box, CU_TENSOR_MAP_SWIZZLE_128B);
    const cuuint64_t stu[1] = {U_PITCH * 16};
    const cuuint32_t boxu[2] = {32, 64};
    encode(fn, &m.u, uaddr, 2, dims, stu, boxu, CU_TENSOR_MAP_SWIZZLE_NONE);
  }
  {
    const cuuint64_t dims[2] = {640, 2048}, st[1] = {1280};
    const cuuint32_t bqm[2] = {64, 128}, bqt[2] = {16, 128}, bom[2] = {64, 16}, bot[2] = {16, 16};
    encode(fn, &m.qm, p.q, 2, dims, st, bqm, CU_TENSOR_MAP_SWIZZLE_128B);
    encode(fn, &m.qt, p.q, 2, dims, st, bqt, CU_TENSOR_MAP_SWIZZLE_32B);
    encode(fn, &m.om, p.out, 2, dims, st, bom, CU_TENSOR_MAP_SWIZZLE_128B);
    encode(fn, &m.ot, p.out, 2, dims, st, bot, CU_TENSOR_MAP_SWIZZLE_32B);
  }
  fused_kernel<<<NCTA, NTHR, SMEM_BYTES>>>(m, p);
}
```

```cpp
#include <cuda.h>
#include <cuda_bf16.h>
#include <cuda_runtime.h>
#include <stdint.h>

namespace {

constexpr int SEQ = 2048, DIM = 640, NCTA = 128, NTHR = 512;

#define TRIG_KB 9
#define KV_KB 2
#define DEV_EXIT 0
#define ATT_GATE 0
#define G_AFTER 0
#define FENCE_LO 0
#define FENCE_HI 0
#define PW1 2
#define PW2 1
#define ENDBAR 0
#define PAD_KB 0
#define Y_ALIAS 1
#define H_EARLY 1
#define NOMB 0
#define SRC_ROT 0
#define WAIT_NS 0
#define WB_TRIG B_USIG
#define G_POS 0
#define TAILF 1
#define T_ISSUE 384
#define T_PF 416
#define T_INIT 448
#define ATT_MERGE 0
#define BMAP 1
#define PRE2 1
#define KV_MIX 0
#define O_DEFER 0
#define TASK0 0x52
#define TASK1 0x3
#define TASK2 0x41
#define HALO_FIRST 1
#define PREV_EARLY 0
#define Y_RB 1
#define O_RB 0
#define ACQ 0
#define U_TMA 0
#define U_GATE 0
#define RF_GATE 0
#define WO_TRIG B_WST
#define WL_TRIG B_WOP
#define WO_GATE 1

constexpr uint32_t STAGE_BYTES = 47104, ST_W = 16384, ST_WT = 40960;
constexpr uint32_t O_BYTES = 20480, WO_BYTES = 12800;
constexpr uint32_t OFF_OA = 0;
constexpr uint32_t OFF_QS = 3 * O_BYTES, OFF_QT = OFF_QS + 16384;
constexpr uint32_t OFF_WC = 81920;
constexpr uint32_t OFF_WA = 94720;
constexpr uint32_t OFF_GATE = 145920;
constexpr uint32_t OFF_TT = 146432;
constexpr uint32_t OFF_KVX = 148480;
constexpr uint32_t OFF_CH3 = 163840;
constexpr uint32_t CH_BYTES = 12288, U_BYTES = 4096;
constexpr uint32_t OFF_FT = 225280, OFF_GT = 229376;
constexpr uint32_t OFF_CH0 = 188416;
constexpr uint32_t OFF_KVS = OFF_CH0, KVS_V = 4480, KVS_BYTES = 8576;
constexpr uint32_t OFF_WS = OFF_WA;
__device__ __forceinline__ uint32_t off_us(int s) { return OFF_CH0 + 4096 * ((0x65320 >> (4 * s)) & 7); }
constexpr uint32_t OFF_YT = 163840;
constexpr uint32_t OFF_BAR = 231936;
constexpr uint32_t SMEM_BYTES = OFF_BAR + 512;

enum : uint32_t {
  B_FULL1 = 0, B_EMPTY1 = 4, B_S3 = 7, B_FULL2 = 52, B_EMPTY2 = 13, B_U = 8, B_GATE = 12, B_HA = 19, B_HB = 20,
  B_ATTN = 21, B_C34 = 22, B_CONV = 23, B_YFULL = 24, B_EPOCH = 25, B_PREP = 26, B_P1 = 27, B_LAST = 28,
  B_E3 = 29, B_OSIG = 30, B_WOP = 31, B_USIG = 32, B_WST = 33, B_KV = 34, B_KVD = 39, B_QF = 17, B_YST = 40,
  B_US = 45, B_YSIG = 50
};
constexpr uint32_t OFF_EPOCH = OFF_BAR + 8 * 51, OFF_D = OFF_BAR + 8 * 60;
__device__ __forceinline__ uint32_t off_o(int j) { return j < 4 ? OFF_OA + j * O_BYTES : j < 6 ? OFF_CH0 + (j - 4) * O_BYTES : OFF_OA + (j - 6) * O_BYTES; }
__device__ __forceinline__ uint32_t off_w(int j) { return j < 4 ? OFF_WA + j * WO_BYTES : j == 4 ? OFF_KVX : j == 5 ? OFF_WC : OFF_WA + (j - 6) * WO_BYTES; }
__device__ __forceinline__ int step_src(int hg, int j) { return SRC_ROT ? (hg + j) & 7 : j == 0 ? hg : j <= hg ? j - 1 : j; }
__device__ __forceinline__ bool tail_first(int hg) { return TAILF && (hg & 3) == 3; }
__device__ __forceinline__ uint32_t off_ch(int c) { return (c < 3 ? OFF_CH0 : OFF_CH3 - 3 * CH_BYTES) + c * CH_BYTES; }

#define U_PITCH 264
__device__ __align__(1024) uint4 g_U[DIM * U_PITCH];
__device__ uint4 g_O[NCTA * 1280];
#define g_Y g_U
constexpr int Y_PITCH = U_PITCH;
__device__ uint4 g_WO[64 * 800];
__device__ uint4 g_halo[NCTA * 2 * 7 * 32];
__device__ float g_gate[SEQ + PAD_KB * 256];
__device__ unsigned g_cnt[32 * (1 + 2 * 16 + 8 + NCTA)];
constexpr int C_LAUNCH = 0, C_PREP = 32, C_Y = 32 * 17, C_W = 32 * 33, C_O = 32 * 41;

#define TSM(cond, slot) do { } while (0)
#define TSIF(cond, slot) do { if (__LINE__ >= FENCE_LO && __LINE__ < FENCE_HI) sched_fence(); } while (0)
__device__ __forceinline__ void sched_fence() {
  asm volatile("{\n.reg .pred p;\n.reg .u32 c;\nmov.u32 c, %%clock;\nsetp.eq.u32 p, c, 0;\n@p st.shared.u32 [%0], c;\n}"
               ::"r"(1024 + OFF_EPOCH + 4) : "memory");
}
#define TS(slot) TSIF(true, slot)

struct Params {
  const __nv_bfloat16 *q, *k, *v, *shift_k, *ssm_k, *ssm_D, *wqkv, *wo, *gate_w;
  __nv_bfloat16* out;
  uint32_t zero;
};

#define POLL_NS 0
constexpr int SPIN_LIMIT = 1 << 17;

__device__ __forceinline__ void mbar_init(uint32_t bar, uint32_t count) {
  asm volatile("mbarrier.init.shared::cta.b64 [%0], %1;" ::"r"(bar), "r"(count) : "memory");
}
__device__ __forceinline__ void mbar_expect_tx(uint32_t bar, uint32_t bytes) {
  asm volatile("mbarrier.arrive.expect_tx.shared::cta.b64 _, [%0], %1;" ::"r"(bar), "r"(bytes) : "memory");
}
__device__ __forceinline__ void mbar_arrive(uint32_t bar) {
  asm volatile("mbarrier.arrive.shared::cta.b64 _, [%0];" ::"r"(bar) : "memory");
}
__device__ __forceinline__ void mbar_wait(uint32_t bar, uint32_t parity) {
  uint32_t ok;
  int spins = 0;
  do {
    if (WAIT_NS)
      asm volatile("{\n.reg .pred p;\nmbarrier.try_wait.parity.shared::cta.b64 p, [%1], %2, %3;\nselp.b32 %0, 1, 0, p;\n}"
                   : "=r"(ok) : "r"(bar), "r"(parity), "r"(WAIT_NS) : "memory");
    else
      asm volatile("{\n.reg .pred p;\nmbarrier.try_wait.parity.shared::cta.b64 p, [%1], %2;\nselp.b32 %0, 1, 0, p;\n}"
                   : "=r"(ok) : "r"(bar), "r"(parity) : "memory");
    if (++spins > SPIN_LIMIT) break;
  } while (!ok);
}
__device__ __forceinline__ unsigned flag_read(const unsigned* p) {
  unsigned v;
  asm volatile("ld.relaxed.gpu.global.u32 %0, [%1];" : "=r"(v) : "l"(p) : "memory");
  return v;
}
__device__ __forceinline__ void flag_poll(const unsigned* p, unsigned target) {
  unsigned v;
  int spins = 0;
  do {
    if (POLL_NS && spins) __nanosleep(POLL_NS);
    asm volatile("ld.relaxed.gpu.global.u32 %0, [%1];" : "=r"(v) : "l"(p) : "memory");
    if (++spins > SPIN_LIMIT) break;
  } while ((int)(v - target) < 0);
}
__device__ __forceinline__ void flag_wait(const unsigned* p, unsigned target) {
  flag_poll(p, target);
  if (ACQ) asm volatile("fence.acquire.gpu;\nfence.proxy.async.global;" ::: "memory");
}
__device__ __forceinline__ void flag_signal(unsigned* p, int n, int lane) {
  if (lane == 0) asm volatile("fence.release.gpu;" ::: "memory");
  __syncwarp();
  if (lane < n) asm volatile("red.relaxed.gpu.global.add.u32 [%0], 1;" ::"l"(p + 32 * lane) : "memory");
}
__device__ __forceinline__ void flag_bump(unsigned* p) {
  asm volatile("red.relaxed.gpu.global.add.u32 [%0], 1;" ::"l"(p) : "memory");
}
__device__ __forceinline__ void fence_async_smem() { asm volatile("fence.proxy.async.shared::cta;" ::: "memory"); }
__device__ __forceinline__ void wg_sync(int id) { asm volatile("bar.sync %0, 128;" ::"r"(id) : "memory"); }

__device__ __forceinline__ void tma_2d(uint32_t dst, const CUtensorMap* tm, int c0, int c1, uint32_t bar) {
  asm volatile("cp.async.bulk.tensor.2d.shared::cluster.global.mbarrier::complete_tx::bytes [%0], [%1, {%3, %4}], [%2];"
               ::"r"(dst), "l"(tm), "r"(bar), "r"(c0), "r"(c1) : "memory");
}
__device__ __forceinline__ void tma_3d(uint32_t dst, const CUtensorMap* tm, int c0, int c1, int c2, uint32_t bar) {
  asm volatile("cp.async.bulk.tensor.3d.shared::cluster.global.mbarrier::complete_tx::bytes [%0], [%1, {%3, %4, %5}], [%2];"
               ::"r"(dst), "l"(tm), "r"(bar), "r"(c0), "r"(c1), "r"(c2) : "memory");
}
__device__ __forceinline__ void bulk_load(uint32_t dst, const void* src, uint32_t bytes, uint32_t bar) {
  asm volatile("cp.async.bulk.shared::cluster.global.mbarrier::complete_tx::bytes [%0], [%1], %2, [%3];"
               ::"r"(dst), "l"(src), "r"(bytes), "r"(bar) : "memory");
}
__device__ __forceinline__ void tm_prefetch(const CUtensorMap* tm) {
  asm volatile("prefetch.tensormap [%0];" ::"l"(tm) : "memory");
}

__device__ __forceinline__ void wg_fence() { asm volatile("wgmma.fence.sync.aligned;" ::: "memory"); }
__device__ __forceinline__ void wg_commit() { asm volatile("wgmma.commit_group.sync.aligned;" ::: "memory"); }
template <int N> __device__ __forceinline__ void wg_wait() { asm volatile("wgmma.wait_group.sync.aligned %0;" ::"n"(N) : "memory"); }
__device__ __forceinline__ uint32_t desc_lo(uint32_t addr, uint32_t lbo) { return ((addr & 0x3FFFF) >> 4) | ((lbo >> 4) << 16); }
constexpr uint32_t desc_hi(uint32_t sbo, uint32_t swz) { return (sbo >> 4) | (swz << 30); }
constexpr uint32_t HI_SW128 = desc_hi(1024, 1), HI_SW64 = desc_hi(512, 2), HI_SW32 = desc_hi(256, 3), HI_NONE = desc_hi(128, 0);
template <int N> __device__ __forceinline__ void pin(float* d) {
#pragma unroll
  for (int i = 0; i < N; i++) asm volatile("" : "+f"(d[i])::"memory");
}

__device__ __forceinline__ uint32_t lds32(uint32_t a) {
  uint32_t v;
  asm volatile("ld.volatile.shared.u32 %0, [%1];" : "=r"(v) : "r"(a) : "memory");
  return v;
}
__device__ __forceinline__ uint4 ldg128(const void* a) {
  uint4 v;
  asm volatile("ld.global.nc.v4.u32 {%0, %1, %2, %3}, [%4];" : "=r"(v.x), "=r"(v.y), "=r"(v.z), "=r"(v.w) : "l"(a) : "memory");
  return v;
}
__device__ __forceinline__ uint2 ldg64(const void* a) {
  uint2 v;
  asm volatile("ld.global.nc.v2.u32 {%0, %1}, [%2];" : "=r"(v.x), "=r"(v.y) : "l"(a) : "memory");
  return v;
}
__device__ __forceinline__ void ldsm4(uint32_t* r, uint32_t a) {
  asm volatile("ldmatrix.sync.aligned.m8n8.x4.shared.b16 {%0, %1, %2, %3}, [%4];"
               : "=r"(r[0]), "=r"(r[1]), "=r"(r[2]), "=r"(r[3]) : "r"(a) : "memory");
}
__device__ __forceinline__ void ldsm4t(uint32_t* r, uint32_t a) {
  asm volatile("ldmatrix.sync.aligned.m8n8.x4.trans.shared.b16 {%0, %1, %2, %3}, [%4];"
               : "=r"(r[0]), "=r"(r[1]), "=r"(r[2]), "=r"(r[3]) : "r"(a) : "memory");
}
__device__ __forceinline__ uint2 lds64(uint32_t a) {
  uint2 v;
  asm volatile("ld.shared.v2.u32 {%0, %1}, [%2];" : "=r"(v.x), "=r"(v.y) : "r"(a) : "memory");
  return v;
}
__device__ __forceinline__ uint4 lds128(uint32_t a) {
  uint4 v;
  asm volatile("ld.shared.v4.u32 {%0, %1, %2, %3}, [%4];" : "=r"(v.x), "=r"(v.y), "=r"(v.z), "=r"(v.w) : "r"(a) : "memory");
  return v;
}
__device__ __forceinline__ void sts128(uint32_t a, uint32_t x, uint32_t y, uint32_t z, uint32_t w) {
  asm volatile("st.shared.v4.u32 [%0], {%1, %2, %3, %4};" ::"r"(a), "r"(x), "r"(y), "r"(z), "r"(w) : "memory");
}
__device__ __forceinline__ void stsm4(uint32_t a, const uint32_t* r) {
  asm volatile("stmatrix.sync.aligned.m8n8.x4.shared.b16 [%0], {%1, %2, %3, %4};" ::"r"(a), "r"(r[0]), "r"(r[1]), "r"(r[2]), "r"(r[3]) : "memory");
}
__device__ __forceinline__ void stsm4t(uint32_t a, const uint32_t* r) {
  asm volatile("stmatrix.sync.aligned.m8n8.x4.trans.shared.b16 [%0], {%1, %2, %3, %4};" ::"r"(a), "r"(r[0]), "r"(r[1]), "r"(r[2]), "r"(r[3]) : "memory");
}
__device__ __forceinline__ uint32_t pack2(float lo, float hi) {
  uint32_t r;
  asm("cvt.rn.bf16x2.f32 %0, %1, %2;" : "=r"(r) : "f"(hi), "f"(lo));
  return r;
}
__device__ __forceinline__ uint32_t movm(uint32_t a) {
  uint32_t d;
  asm volatile("movmatrix.sync.aligned.m8n8.trans.b16 %0, %1;" : "=r"(d) : "r"(a));
  return d;
}
__device__ __forceinline__ uint32_t bmul(uint32_t a, uint32_t b) {
  uint32_t d;
  asm("mul.rn.bf16x2 %0, %1, %2;" : "=r"(d) : "r"(a), "r"(b));
  return d;
}
__device__ __forceinline__ uint32_t badd(uint32_t a, uint32_t b) {
  uint32_t d;
  asm("add.rn.bf16x2 %0, %1, %2;" : "=r"(d) : "r"(a), "r"(b));
  return d;
}
__device__ __forceinline__ uint32_t bfma(uint32_t a, uint32_t b, uint32_t c) {
  uint32_t d;
  asm("fma.rn.bf16x2 %0, %1, %2, %3;" : "=r"(d) : "r"(a), "r"(b), "r"(c));
  return d;
}
__device__ __forceinline__ float bf_lo(uint32_t x) { return __uint_as_float(x << 16); }
__device__ __forceinline__ float bf_hi(uint32_t x) { return __uint_as_float(x & 0xFFFF0000u); }
__device__ __forceinline__ float ex2(float x) {
  float y;
  asm("ex2.approx.ftz.f32 %0, %1;" : "=f"(y) : "f"(x));
  return y;
}
__device__ __forceinline__ float rcp(float x) {
  float y;
  asm("rcp.approx.ftz.f32 %0, %1;" : "=f"(y) : "f"(x));
  return y;
}
__device__ __forceinline__ void mma16816(float* d, uint32_t a0, uint32_t a1, uint32_t a2, uint32_t a3, uint32_t b0, uint32_t b1) {
  asm volatile("mma.sync.aligned.m16n8k16.row.col.f32.bf16.bf16.f32 {%0, %1, %2, %3}, {%4, %5, %6, %7}, {%8, %9}, {%0, %1, %2, %3};"
               : "+f"(d[0]), "+f"(d[1]), "+f"(d[2]), "+f"(d[3])
               : "r"(a0), "r"(a1), "r"(a2), "r"(a3), "r"(b0), "r"(b1));
}
__device__ __forceinline__ void mma1688(float* d, uint32_t a0, uint32_t a1, uint32_t b0) {
  asm volatile("mma.sync.aligned.m16n8k8.row.col.f32.bf16.bf16.f32 {%0, %1, %2, %3}, {%4, %5}, {%6}, {%0, %1, %2, %3};"
               : "+f"(d[0]), "+f"(d[1]), "+f"(d[2]), "+f"(d[3])
               : "r"(a0), "r"(a1), "r"(b0));
}

template <int N> struct WgRS;
template <int N> struct WgSST;
template <> struct WgRS<32> {
  template <uint32_t HB>
  static __device__ __forceinline__ void mma(float* d, const uint32_t* a, uint32_t db) {
    asm volatile("{\n.reg .pred p;\n.reg .b64 db;\nsetp.ne.b32 p, %22, 0;\n"
      "mov.b64 db, {%20, %21};\n"
      "wgmma.mma_async.sync.aligned.m64n32k16.f32.bf16.bf16 {"
      "%0, %1, %2, %3, %4, %5, %6, %7, %8, %9, %10, %11, %12, %13, %14, %15"
      "}, {%16, %17, %18, %19}, db, p, 1, 1, 1;\n}\n"
      : "+f"(d[0]), "+f"(d[1]), "+f"(d[2]), "+f"(d[3]), "+f"(d[4]), "+f"(d[5]), "+f"(d[6]), "+f"(d[7]),
        "+f"(d[8]), "+f"(d[9]), "+f"(d[10]), "+f"(d[11]), "+f"(d[12]), "+f"(d[13]), "+f"(d[14]), "+f"(d[15])
      : "r"(a[0]), "r"(a[1]), "r"(a[2]), "r"(a[3]), "r"(db), "n"(HB), "n"(1));
  }
  template <uint32_t HB>
  static __device__ __forceinline__ void set(float* d, const uint32_t* a, uint32_t db) {
    asm volatile("{\n.reg .pred p;\n.reg .b64 db;\nsetp.ne.b32 p, %22, 0;\n"
      "mov.b64 db, {%20, %21};\n"
      "wgmma.mma_async.sync.aligned.m64n32k16.f32.bf16.bf16 {"
      "%0, %1, %2, %3, %4, %5, %6, %7, %8, %9, %10, %11, %12, %13, %14, %15"
      "}, {%16, %17, %18, %19}, db, p, 1, 1, 1;\n}\n"
      : "=f"(d[0]), "=f"(d[1]), "=f"(d[2]), "=f"(d[3]), "=f"(d[4]), "=f"(d[5]), "=f"(d[6]), "=f"(d[7]),
        "=f"(d[8]), "=f"(d[9]), "=f"(d[10]), "=f"(d[11]), "=f"(d[12]), "=f"(d[13]), "=f"(d[14]), "=f"(d[15])
      : "r"(a[0]), "r"(a[1]), "r"(a[2]), "r"(a[3]), "r"(db), "n"(HB), "n"(0));
  }
};
template <> struct WgRS<64> {
  template <uint32_t HB>
  static __device__ __forceinline__ void mma(float* d, const uint32_t* a, uint32_t db) {
    asm volatile("{\n.reg .pred p;\n.reg .b64 db;\nsetp.ne.b32 p, %38, 0;\n"
      "mov.b64 db, {%36, %37};\n"
      "wgmma.mma_async.sync.aligned.m64n64k16.f32.bf16.bf16 {"
      "%0, %1, %2, %3, %4, %5, %6, %7, %8, %9, %10, %11, %12, %13, %14, %15, "
      "%16, %17, %18, %19, %20, %21, %22, %23, %24, %25, %26, %27, %28, %29, %30, %31"
      "}, {%32, %33, %34, %35}, db, p, 1, 1, 1;\n}\n"
      : "+f"(d[0]), "+f"(d[1]), "+f"(d[2]), "+f"(d[3]), "+f"(d[4]), "+f"(d[5]), "+f"(d[6]), "+f"(d[7]),
        "+f"(d[8]), "+f"(d[9]), "+f"(d[10]), "+f"(d[11]), "+f"(d[12]), "+f"(d[13]), "+f"(d[14]), "+f"(d[15]),
        "+f"(d[16]), "+f"(d[17]), "+f"(d[18]), "+f"(d[19]), "+f"(d[20]), "+f"(d[21]), "+f"(d[22]), "+f"(d[23]),
        "+f"(d[24]), "+f"(d[25]), "+f"(d[26]), "+f"(d[27]), "+f"(d[28]), "+f"(d[29]), "+f"(d[30]), "+f"(d[31])
      : "r"(a[0]), "r"(a[1]), "r"(a[2]), "r"(a[3]), "r"(db), "n"(HB), "n"(1));
  }
  template <uint32_t HB>
  static __device__ __forceinline__ void set(float* d, const uint32_t* a, uint32_t db) {
    asm volatile("{\n.reg .pred p;\n.reg .b64 db;\nsetp.ne.b32 p, %38, 0;\n"
      "mov.b64 db, {%36, %37};\n"
      "wgmma.mma_async.sync.aligned.m64n64k16.f32.bf16.bf16 {"
      "%0, %1, %2, %3, %4, %5, %6, %7, %8, %9, %10, %11, %12, %13, %14, %15, "
      "%16, %17, %18, %19, %20, %21, %22, %23, %24, %25, %26, %27, %28, %29, %30, %31"
      "}, {%32, %33, %34, %35}, db, p, 1, 1, 1;\n}\n"
      : "=f"(d[0]), "=f"(d[1]), "=f"(d[2]), "=f"(d[3]), "=f"(d[4]), "=f"(d[5]), "=f"(d[6]), "=f"(d[7]),
        "=f"(d[8]), "=f"(d[9]), "=f"(d[10]), "=f"(d[11]), "=f"(d[12]), "=f"(d[13]), "=f"(d[14]), "=f"(d[15]),
        "=f"(d[16]), "=f"(d[17]), "=f"(d[18]), "=f"(d[19]), "=f"(d[20]), "=f"(d[21]), "=f"(d[22]), "=f"(d[23]),
        "=f"(d[24]), "=f"(d[25]), "=f"(d[26]), "=f"(d[27]), "=f"(d[28]), "=f"(d[29]), "=f"(d[30]), "=f"(d[31])
      : "r"(a[0]), "r"(a[1]), "r"(a[2]), "r"(a[3]), "r"(db), "n"(HB), "n"(0));
  }
};
template <> struct WgSST<48> {
  template <uint32_t HA, uint32_t HB>
  static __device__ __forceinline__ void mma(float* d, uint32_t da, uint32_t db, int sc) {
    asm volatile("{\n.reg .pred p;\n.reg .b64 da, db;\nsetp.ne.b32 p, %28, 0;\n"
      "mov.b64 da, {%24, %25};\nmov.b64 db, {%26, %27};\n"
      "wgmma.mma_async.sync.aligned.m64n48k16.f32.bf16.bf16 {"
      "%0, %1, %2, %3, %4, %5, %6, %7, %8, %9, %10, %11, %12, %13, %14, %15, "
      "%16, %17, %18, %19, %20, %21, %22, %23"
      "}, da, db, p, 1, 1, 0, 1;\n}\n"
      : "+f"(d[0]), "+f"(d[1]), "+f"(d[2]), "+f"(d[3]), "+f"(d[4]), "+f"(d[5]), "+f"(d[6]), "+f"(d[7]),
        "+f"(d[8]), "+f"(d[9]), "+f"(d[10]), "+f"(d[11]), "+f"(d[12]), "+f"(d[13]), "+f"(d[14]), "+f"(d[15]),
        "+f"(d[16]), "+f"(d[17]), "+f"(d[18]), "+f"(d[19]), "+f"(d[20]), "+f"(d[21]), "+f"(d[22]), "+f"(d[23])
      : "r"(da), "n"(HA), "r"(db), "n"(HB), "r"(sc));
  }
};
template <> struct WgSST<80> {
  template <uint32_t HA, uint32_t HB>
  static __device__ __forceinline__ void mma(float* d, uint32_t da, uint32_t db, int sc) {
    asm volatile("{\n.reg .pred p;\n.reg .b64 da, db;\nsetp.ne.b32 p, %44, 0;\n"
      "mov.b64 da, {%40, %41};\nmov.b64 db, {%42, %43};\n"
      "wgmma.mma_async.sync.aligned.m64n80k16.f32.bf16.bf16 {"
      "%0, %1, %2, %3, %4, %5, %6, %7, %8, %9, %10, %11, %12, %13, %14, %15, "
      "%16, %17, %18, %19, %20, %21, %22, %23, %24, %25, %26, %27, %28, %29, %30, %31, "
      "%32, %33, %34, %35, %36, %37, %38, %39"
      "}, da, db, p, 1, 1, 0, 1;\n}\n"
      : "+f"(d[0]), "+f"(d[1]), "+f"(d[2]), "+f"(d[3]), "+f"(d[4]), "+f"(d[5]), "+f"(d[6]), "+f"(d[7]),
        "+f"(d[8]), "+f"(d[9]), "+f"(d[10]), "+f"(d[11]), "+f"(d[12]), "+f"(d[13]), "+f"(d[14]), "+f"(d[15]),
        "+f"(d[16]), "+f"(d[17]), "+f"(d[18]), "+f"(d[19]), "+f"(d[20]), "+f"(d[21]), "+f"(d[22]), "+f"(d[23]),
        "+f"(d[24]), "+f"(d[25]), "+f"(d[26]), "+f"(d[27]), "+f"(d[28]), "+f"(d[29]), "+f"(d[30]), "+f"(d[31]),
        "+f"(d[32]), "+f"(d[33]), "+f"(d[34]), "+f"(d[35]), "+f"(d[36]), "+f"(d[37]), "+f"(d[38]), "+f"(d[39])
      : "r"(da), "n"(HA), "r"(db), "n"(HB), "r"(sc));
  }
};
template <> struct WgSST<192> {
  template <uint32_t HA, uint32_t HB>
  static __device__ __forceinline__ void mma(float* d, uint32_t da, uint32_t db, int sc) {
    asm volatile("{\n.reg .pred p;\n.reg .b64 da, db;\nsetp.ne.b32 p, %100, 0;\n"
      "mov.b64 da, {%96, %97};\nmov.b64 db, {%98, %99};\n"
      "wgmma.mma_async.sync.aligned.m64n192k16.f32.bf16.bf16 {"
      "%0, %1, %2, %3, %4, %5, %6, %7, %8, %9, %10, %11, %12, %13, %14, %15, "
      "%16, %17, %18, %19, %20, %21, %22, %23, %24, %25, %26, %27, %28, %29, %30, %31, "
      "%32, %33, %34, %35, %36, %37, %38, %39, %40, %41, %42, %43, %44, %45, %46, %47, "
      "%48, %49, %50, %51, %52, %53, %54, %55, %56, %57, %58, %59, %60, %61, %62, %63, "
      "%64, %65, %66, %67, %68, %69, %70, %71, %72, %73, %74, %75, %76, %77, %78, %79, "
      "%80, %81, %82, %83, %84, %85, %86, %87, %88, %89, %90, %91, %92, %93, %94, %95"
      "}, da, db, p, 1, 1, 0, 1;\n}\n"
      : "+f"(d[0]), "+f"(d[1]), "+f"(d[2]), "+f"(d[3]), "+f"(d[4]), "+f"(d[5]), "+f"(d[6]), "+f"(d[7]),
        "+f"(d[8]), "+f"(d[9]), "+f"(d[10]), "+f"(d[11]), "+f"(d[12]), "+f"(d[13]), "+f"(d[14]), "+f"(d[15]),
        "+f"(d[16]), "+f"(d[17]), "+f"(d[18]), "+f"(d[19]), "+f"(d[20]), "+f"(d[21]), "+f"(d[22]), "+f"(d[23]),
        "+f"(d[24]), "+f"(d[25]), "+f"(d[26]), "+f"(d[27]), "+f"(d[28]), "+f"(d[29]), "+f"(d[30]), "+f"(d[31]),
        "+f"(d[32]), "+f"(d[33]), "+f"(d[34]), "+f"(d[35]), "+f"(d[36]), "+f"(d[37]), "+f"(d[38]), "+f"(d[39]),
        "+f"(d[40]), "+f"(d[41]), "+f"(d[42]), "+f"(d[43]), "+f"(d[44]), "+f"(d[45]), "+f"(d[46]), "+f"(d[47]),
        "+f"(d[48]), "+f"(d[49]), "+f"(d[50]), "+f"(d[51]), "+f"(d[52]), "+f"(d[53]), "+f"(d[54]), "+f"(d[55]),
        "+f"(d[56]), "+f"(d[57]), "+f"(d[58]), "+f"(d[59]), "+f"(d[60]), "+f"(d[61]), "+f"(d[62]), "+f"(d[63]),
        "+f"(d[64]), "+f"(d[65]), "+f"(d[66]), "+f"(d[67]), "+f"(d[68]), "+f"(d[69]), "+f"(d[70]), "+f"(d[71]),
        "+f"(d[72]), "+f"(d[73]), "+f"(d[74]), "+f"(d[75]), "+f"(d[76]), "+f"(d[77]), "+f"(d[78]), "+f"(d[79]),
        "+f"(d[80]), "+f"(d[81]), "+f"(d[82]), "+f"(d[83]), "+f"(d[84]), "+f"(d[85]), "+f"(d[86]), "+f"(d[87]),
        "+f"(d[88]), "+f"(d[89]), "+f"(d[90]), "+f"(d[91]), "+f"(d[92]), "+f"(d[93]), "+f"(d[94]), "+f"(d[95])
      : "r"(da), "n"(HA), "r"(db), "n"(HB), "r"(sc));
  }
};

struct FftConst {
  uint32_t f[2][4], fi[4][4];
  uint32_t ta[2][2], tb[2][2];
};
__device__ __forceinline__ void cis(int m, float scale, float& c, float& s) {
  const float a = (float)m * (-6.283185307179586f * scale);
  c = __cosf(a);
  s = __sinf(a);
}
__device__ __forceinline__ void fft_tables(uint32_t (&v)[12], int tw) {
  const int row = tw >> 2, ch = tw & 3;
#pragma unroll
  for (int i = 0; i < 4; i++) {
    float c[2], s[2], x[2];
#pragma unroll
    for (int e = 0; e < 2; e++) {
      cis((((32 * (8 * ch + 2 * i + e) + 15) * (4 * row - 63) + 2048) & 4095) - 2048, 1.f / 4096, c[e], s[e]);
      float gc, gs;
      cis((((row & 15) * (8 * (ch & 1) + 2 * i + e) + 8) & 15) - 8, 1.f / 16, gc, gs);
      x[e] = (row >> 4) == (ch >> 1) ? gc : (ch >> 1) ? gs : -gs;
    }
    v[i] = pack2(c[0] * 0.125f, c[1] * 0.125f);
    v[4 + i] = pack2(s[0] * 0.125f, s[1] * 0.125f);
    v[8 + i] = pack2(x[0], x[1]);
  }
#pragma unroll
  for (int i = 0; i < 12; i++) asm volatile("" : "+r"(v[i]));
}
__device__ __forceinline__ void fft_tables_store(const uint32_t (&v)[12], uint32_t sb, int tw) {
  const int row = tw >> 2;
  const uint32_t x = ((tw ^ (row >> 1)) & 3) << 4, a = sb + OFF_FT + (16 * (row >> 3) + (row & 7)) * 64 + x;
  sts128(a, v[0], v[1], v[2], v[3]);
  sts128(a + 512, v[4], v[5], v[6], v[7]);
  sts128(sb + OFF_GT + row * 64 + x, v[8], v[9], v[10], v[11]);
}
__device__ __forceinline__ void fft_twiddles(uint32_t (&v)[2], int tw) {
  float a[2], s[2];
#pragma unroll
  for (int i = 0; i < 2; i++) {
    float c;
    cis((2 * (2 * (tw & 3) + i) - 15) * (4 * (tw >> 2) - 63), 1.f / 4096, c, s[i]);
    a[i] = __fdividef(-s[i], 1.f + c);
  }
  v[0] = pack2(a[0], a[1]);
  v[1] = pack2(s[0], s[1]);
  asm volatile("" : "+r"(v[0]), "+r"(v[1]));
}
__device__ __forceinline__ void fft_matrices(FftConst& k, uint32_t sb, int w, int lane) {
  const uint32_t x = (lane >> 1) & 3;
  const uint2 t0 = lds64(sb + OFF_TT + 256 * w + 8 * lane), t1 = lds64(sb + OFF_TT + 256 * w + 8 * (lane ^ 3));
  k.ta[0][0] = t0.x;
  k.tb[0][0] = t0.y;
  k.ta[1][1] = __byte_perm(t1.x, 0, 0x1032);
  k.tb[1][1] = __byte_perm(t1.y, 0, 0x1032);
#pragma unroll
  for (int j = 0; j < 2; j++) {
    k.ta[1 - j][j] = k.ta[j][j] ^ 0x80008000u;
    k.tb[1 - j][j] = k.tb[j][j] ^ 0x80008000u;
    asm volatile("" : "+r"(k.ta[0][j]), "+r"(k.tb[0][j]), "+r"(k.ta[1][j]), "+r"(k.tb[1][j]));
  }
#pragma unroll
  for (int i = 0; i < 2; i++) {
    ldsm4(k.f[i], sb + OFF_FT + (16 * w + (lane & 15)) * 64 + (((2 * i + (lane >> 4)) ^ x) << 4));
    ldsm4t(k.fi[i], sb + OFF_FT + (32 * i + lane) * 64 + ((w ^ x) << 4));
#pragma unroll
    for (int j = 0; j < 4; j++) {
      k.fi[2 + i][j] = (j & 1) ? k.fi[i][j - 1] ^ 0x80008000u : k.fi[i][j + 1];
      asm volatile("" : "+r"(k.fi[2 + i][j]));
    }
  }
}
__device__ __forceinline__ void rot(uint32_t& x, uint32_t& y, uint32_t a, uint32_t b) {
  x = bfma(a, y, x);
  y = bfma(b, x, y);
  x = bfma(a, y, x);
}
__device__ __forceinline__ void twiddle_fwd(uint32_t (&a)[4][4], float* d, const FftConst& k) {
#pragma unroll
  for (int q = 0; q < 4; q++)
#pragma unroll
    for (int j = 0; j < 2; j++) {
      const float* x = d + 8 * q + 4 * j;
      uint32_t re = pack2(x[0], x[1]), im = pack2(x[2], x[3]);
      rot(re, im, k.ta[0][j], k.tb[0][j]);
      a[q & 2][2 * j + (q & 1)] = re;
      a[(q & 2) + 1][2 * j + (q & 1)] = im;
    }
}
__device__ __forceinline__ void g_step(float* d, const uint32_t (&a)[4][4], uint32_t dre, uint32_t dim) {
  WgRS<32>::set<HI_SW64>(d, a[0], dre);
  WgRS<32>::set<HI_SW64>(d + 16, a[2], dre);
  WgRS<32>::mma<HI_SW64>(d, a[1], dim);
  WgRS<32>::mma<HI_SW64>(d + 16, a[3], dim);
  wg_commit();
}

__device__ __forceinline__ void conv_channel(const FftConst& k, uint32_t sb, int c, int wg, int w, int lane) {
  const uint32_t cb = sb + off_ch(c), bars = sb + OFF_BAR;
  const uint32_t du = desc_lo(cb, 1024), dg = desc_lo(sb + OFF_GT, 16), dz = desc_lo(cb + U_BYTES, 16);
  float U[32], H[32];
  uint32_t a[4][4], e[4][4];
  const float dv = __uint_as_float(lds32(sb + OFF_D + 4 * c));
  wg_fence();
  WgRS<64>::set<HI_SW32>(H, k.f[0], du + 256);
  WgRS<64>::mma<HI_SW32>(H, k.f[1], du + 256 + 32);
  wg_commit();
  wg_wait<0>();
  pin<32>(H);
  twiddle_fwd(a, H, k);
  if (ATT_GATE && H_EARLY) mbar_wait(bars + 8 * B_ATTN, 0);
  mbar_wait(bars + 8 * (B_U + (c < 3 ? c : 3)), 0);
  TSM(w == 0 && c < 3, 7 + wg);
  wg_fence();
  WgRS<64>::set<HI_SW32>(U, k.f[0], du);
  WgRS<64>::mma<HI_SW32>(U, k.f[1], du + 32);
  wg_commit();
  g_step(H, a, dg, dg + 64);
  wg_wait<1>();
  pin<32>(U);
  twiddle_fwd(e, U, k);
  wg_fence();
  g_step(U, e, dg, dg + 64);
  wg_wait<0>();
  pin<32>(U);
  pin<32>(H);
#pragma unroll
  for (int j = 0; j < 2; j++) {
    float pr[4][2], pi[4][2];
#pragma unroll
    for (int x = 0; x < 2; x++) {
      H[4 * j + x] += dv;
#pragma unroll
      for (int m = 0; m < 4; m++) {
#pragma unroll
        for (int q = 0; q <= m; q++) {
          const int ih = 16 * (q >> 1) + 2 * (q & 1) + 4 * j + x, iu = 16 * ((m - q) >> 1) + 2 * ((m - q) & 1) + 4 * j + x;
          pr[m][x] = q ? fmaf(H[ih], U[iu], pr[m][x]) : H[ih] * U[iu];
          pi[m][x] = q ? fmaf(H[ih], U[iu + 8], pi[m][x]) : H[ih] * U[iu + 8];
          pr[m][x] = fmaf(-H[ih + 8], U[iu + 8], pr[m][x]);
          pi[m][x] = fmaf(H[ih + 8], U[iu], pi[m][x]);
        }
      }
    }
#pragma unroll
    for (int m = 0; m < 4; m++) {
      a[m & 2][2 * j + (m & 1)] = pack2(pr[m][0], pr[m][1]);
      a[(m & 2) + 1][2 * j + (m & 1)] = pack2(pi[m][0], pi[m][1]);
    }
  }
  wg_fence();
  g_step(U, a, dg + 64, dg);
  const uint32_t za = cb + U_BYTES + (8 * w + (lane & 7)) * 128 + (((lane >> 3) ^ (lane & 7)) << 4);
  const uint32_t ya = cb + (lane >> 4) * 1024 + (8 * w + (lane & 7)) * 32 + ((((lane >> 3) ^ (lane >> 2)) & 1) << 4);
  wg_sync(1 + wg);
  wg_wait<0>();
  pin<32>(U);
  TSIF(w == 0, 80 + c);
#pragma unroll
  for (int p = 0; p < 2; p++) {
#pragma unroll
    for (int i = 0; i < 4; i++) {
      const int j = i & 1;
      const float* x = U + 16 * p + 4 * j + (i & 2);
      e[p][i] = pack2(x[8], x[9]);
      e[2 + p][i] = pack2(x[0], x[1]);
      rot(e[p][i], e[2 + p][i], k.ta[1][j], k.tb[1][j]);
    }
    stsm4(za ^ (64 * p), e[p]);
    stsm4((za ^ (64 * p)) + 4096, e[2 + p]);
  }
  fence_async_smem();
  wg_sync(1 + wg);
  wg_fence();
  WgRS<64>::set<HI_SW128>(H, k.fi[0], dz);
#pragma unroll
  for (int ks = 1; ks < 4; ks++) WgRS<64>::mma<HI_SW128>(H, k.fi[ks], dz + 128 * ks);
  wg_commit();
  wg_wait<0>();
  pin<32>(H);
  TSIF(w == 0, 88 + c);
#pragma unroll
  for (int j = 0; j < 8; j++)
    a[j >> 2][j & 3] = j < 2 ? pack2(H[4 * j], H[4 * j + 1]) : pack2(H[4 * j] + H[4 * j - 6], H[4 * j + 1] + H[4 * j - 5]);
  stsm4(ya, a[0]);
  stsm4(ya + 2048, a[1]);
  fence_async_smem();
  __syncwarp();
}

__device__ __forceinline__ void prep_slab(uint4* res, const uint2* sw, uint32_t sb, int slab, int w, int lane) {
  const int t = lane & 3, tp = (lane & 7) >> 1, pos = 8 * tp + 2 * (((lane >> 3) + tp) & 3) + (lane & 1);
  const uint32_t base = sb + OFF_KVS + slab * KVS_BYTES + pos * 128;
  uint32_t kk[2][4][4], vv[2][4];
  mbar_wait(sb + OFF_BAR + 8 * (B_KV + slab), 0);
#pragma unroll
  for (int h = 0; h < 2; h++) {
#pragma unroll
    for (int j = 0; j < 4; j++) {
      const uint32_t a = base + 128 * j;
      ldsm4t(kk[h][j], a + (((w + 4 * h) ^ ((a >> 7) & 7)) << 4));
    }
    const uint32_t a = base + KVS_V;
    ldsm4t(vv[h], a + (((w + 4 * h) ^ ((a >> 7) & 7)) << 4));
  }
#pragma unroll
  for (int h = 0; h < 2; h++) {
    uint32_t (&k)[4][4] = kk[h];
    uint32_t (&v)[4] = vv[h];
    const uint32_t w0 = __byte_perm(sw[h].x, 0, 0x1010), w1 = __byte_perm(sw[h].x, 0, 0x3232);
    const uint32_t w2 = __byte_perm(sw[h].y, 0, 0x1010), w3 = __byte_perm(sw[h].y, 0, 0x3232);
#pragma unroll
    for (int m = 0; m < 4; m++)
      v[m] = bmul(badd(badd(badd(bmul(k[0][m], w3), bmul(k[1][m], w2)), bmul(k[2][m], w1)), bmul(k[3][m], w0)), v[m]);
    uint32_t a[4];
#pragma unroll
    for (int m = 0; m < 4; m++) a[m] = (t & 1) ? v[(m + 3) & 3] : v[m];
    res[h] = (t & 2) ? make_uint4(a[2], a[3], a[0], a[1]) : make_uint4(a[0], a[1], a[2], a[3]);
  }
}

__device__ __forceinline__ void prep_gate(const Params& p, int b, int w, int lane) {
  uint2 gw[5], x[4][5];
#pragma unroll
  for (int j = 0; j < 5; j++) gw[j] = ldg64(reinterpret_cast<const uint2*>(p.gate_w) + lane + 32 * j);
#pragma unroll
  for (int i = 0; i < 4; i++)
#pragma unroll
    for (int j = 0; j < 5; j++)
      x[i][j] = ldg64(reinterpret_cast<const uint2*>(p.q) + (16 * b + 4 * w + i) * (DIM / 4) + lane + 32 * j);
  float s[4];
#pragma unroll
  for (int i = 0; i < 4; i++) {
    s[i] = 0.f;
#pragma unroll
    for (int j = 0; j < 5; j++) {
      const uint32_t m0 = bmul(x[i][j].x, gw[j].x), m1 = bmul(x[i][j].y, gw[j].y);
      s[i] += (bf_lo(m0) + bf_hi(m0)) + (bf_lo(m1) + bf_hi(m1));
    }
  }
  const bool h = lane & 16, q = lane & 8;
  const float a = (h ? s[2] : s[0]) + __shfl_xor_sync(0xffffffffu, h ? s[0] : s[2], 16);
  const float c = (h ? s[3] : s[1]) + __shfl_xor_sync(0xffffffffu, h ? s[1] : s[3], 16);
  float z = (q ? c : a) + __shfl_xor_sync(0xffffffffu, q ? a : c, 8);
#pragma unroll
  for (int o = 4; o > 0; o >>= 1) z += __shfl_xor_sync(0xffffffffu, z, o);
  z = bf_lo(pack2(z, 0.f));
  if ((lane & 7) == 0) g_gate[16 * b + 4 * w + (lane >> 3)] = bf_lo(pack2(__fdividef(1.f, 1.f + __expf(-z)), 0.f));
}

__device__ __forceinline__ uint32_t bmax(uint32_t a, uint32_t b) {
  uint32_t d;
  asm("max.bf16x2 %0, %1, %2;" : "=r"(d) : "r"(a), "r"(b));
  return d;
}
__device__ __forceinline__ void softmax_two(const float (&l)[2][2], uint32_t& p0, uint32_t& p1) {
  constexpr float kScale = 0.22360679774997896f, kLog2e = 1.4426950408889634f;
  const uint32_t r0 = pack2(l[0][0], l[1][0]), r1 = pack2(l[0][1], l[1][1]);
  const uint32_t x0 = pack2(bf_lo(r0) * kScale, bf_hi(r0) * kScale), x1 = pack2(bf_lo(r1) * kScale, bf_hi(r1) * kScale);
  uint32_t m = bmax(x0, x1);
  m = bmax(m, __shfl_xor_sync(0xffffffffu, m, 1));
  m = bmax(m, __shfl_xor_sync(0xffffffffu, m, 2));
  const float m0 = bf_lo(m) * kLog2e, m1 = bf_hi(m) * kLog2e;
  p0 = pack2(ex2(bf_lo(x0) * kLog2e - m0), ex2(bf_lo(x1) * kLog2e - m0));
  p1 = pack2(ex2(bf_hi(x0) * kLog2e - m1), ex2(bf_hi(x1) * kLog2e - m1));
}

__device__ __forceinline__ void halo_read(uint32_t (&kpv)[10], uint32_t (&vpv)[10], uint32_t (&tg)[7], const uint4* hp) {
#pragma unroll
  for (int j = 0; j < 7; j++) {
    uint32_t x0, x1, x2;
    asm volatile("ld.relaxed.gpu.global.v4.u32 {%0, %1, %2, %3}, [%4];"
                 : "=r"(x0), "=r"(x1), "=r"(x2), "=r"(tg[j]) : "l"(hp + 32 * j) : "memory");
    if (j < 4) kpv[3 * j] = x0; else vpv[3 * j - 10] = x0;
    if (j < 3) kpv[3 * j + 1] = x1; else vpv[3 * j - 9] = x1;
    if (j < 3) kpv[3 * j + 2] = x2; else if (j < 6) vpv[3 * j - 8] = x2;
  }
}

template <int ROT>
__device__ __forceinline__ void pack_qkv(const float* acc, uint32_t (&qlo)[10], uint32_t (&qhi)[10], uint32_t (&klo)[10],
                                         uint32_t (&khi)[10], uint32_t (&vlo)[10], uint32_t (&vhi)[10]) {
#pragma unroll
  for (int j = 0; j < 10; j++) {
    const int x = (j + ROT) % 10, tq = x < 8 ? x : 16 + x, tk = x < 8 ? 8 + x : 18 + x, tv = x < 8 ? 16 + x : 20 + x;
    khi[j] = pack2(acc[4 * tk + 2], acc[4 * tk + 3]);
    vhi[j] = movm(pack2(acc[4 * tv + 2], acc[4 * tv + 3]));
    qlo[j] = pack2(acc[4 * tq], acc[4 * tq + 1]);
    qhi[j] = pack2(acc[4 * tq + 2], acc[4 * tq + 3]);
    klo[j] = pack2(acc[4 * tk], acc[4 * tk + 1]);
    vlo[j] = pack2(acc[4 * tv], acc[4 * tv + 1]);
    asm volatile("" : "+r"(khi[j]), "+r"(qlo[j]), "+r"(qhi[j]), "+r"(klo[j]), "+r"(vlo[j]));
  }
}

template <int ROT> __device__ __forceinline__ void halo_send(const float* acc, uint4* ho, uint32_t tag) {
#pragma unroll
  for (int j = 0; j < 7; j++) {
    uint32_t x[3];
#pragma unroll
    for (int e = 0; e < 3; e++) {
      const int i = 3 * j + e, y = (i % 10 + ROT) % 10, tk = y < 8 ? 8 + y : 18 + y, tv = y < 8 ? 16 + y : 20 + y;
      x[e] = i < 10 ? pack2(acc[4 * tk + 2], acc[4 * tk + 3]) : i < 20 ? movm(pack2(acc[4 * tv + 2], acc[4 * tv + 3])) : 0u;
    }
    asm volatile("st.relaxed.gpu.global.v4.u32 [%0], {%1, %2, %3, %4};" ::"l"(ho + 32 * j), "r"(x[0]), "r"(x[1]), "r"(x[2]), "r"(tag) : "memory");
  }
}

__device__ __forceinline__ void attention(float* acc, uint32_t sb, int b, int par, int w, int lane, uint32_t tag) {
  const int g = lane >> 2, t = lane & 3;
  uint32_t klo[10], khi[10], vlo[10], vhi[10], qlo[10], qhi[10], kpv[10], vpv[10];
  if (HALO_FIRST && w == 3 && b < NCTA - 8) {
    uint4* ho = g_halo + (b * 2 + par) * 224 + lane;
    if (tail_first(b & 7)) halo_send<8>(acc, ho, tag);
    else halo_send<0>(acc, ho, tag);
    TSIF(par == 0, 76);
    pin<120>(acc);
  }
  if (tail_first(b & 7)) pack_qkv<8>(acc, qlo, qhi, klo, khi, vlo, vhi);
  else pack_qkv<0>(acc, qlo, qhi, klo, khi, vlo, vhi);
  const uint32_t xa = sb + OFF_KVX + (par * 3) * 2560 + lane * 16;
  if (w < 3) {
    sts128(xa + w * 2560, khi[0], khi[1], khi[2], khi[3]);
    sts128(xa + w * 2560 + 512, khi[4], khi[5], khi[6], khi[7]);
    sts128(xa + w * 2560 + 1024, khi[8], khi[9], vhi[0], vhi[1]);
    sts128(xa + w * 2560 + 1536, vhi[2], vhi[3], vhi[4], vhi[5]);
    sts128(xa + w * 2560 + 2048, vhi[6], vhi[7], vhi[8], vhi[9]);
  } else if (!HALO_FIRST && b < NCTA - 8) {
    uint4* ho = g_halo + (b * 2 + par) * 224 + lane;
#pragma unroll
    for (int j = 0; j < 7; j++) {
      const uint32_t x0 = j < 4 ? khi[3 * j] : vhi[3 * j - 10], x1 = j < 3 ? khi[3 * j + 1] : vhi[3 * j - 9];
      const uint32_t x2 = j < 3 ? khi[3 * j + 2] : j < 6 ? vhi[3 * j - 8] : 0u;
      asm volatile("st.relaxed.gpu.global.v4.u32 [%0], {%1, %2, %3, %4};" ::"l"(ho + 32 * j), "r"(x0), "r"(x1), "r"(x2), "r"(tag) : "memory");
    }
  }
  TSIF(par == 0 && w == 1, 64);
  TSIF(par == 0 && w == 3 && !HALO_FIRST, 76);
#pragma unroll
  for (int j = 0; j < 10; j++) vlo[j] = movm(vlo[j]);
  const bool far0 = 2 * t > g, far1 = 2 * t + 1 > g;
  const uint32_t mfar = (far0 ? 0x0000FFFFu : 0u) | (far1 ? 0xFFFF0000u : 0u);
  float slo[4][2], shi[4][2], lg[2][2];
  uint32_t phi[4], plo[4], qml[4], qmh[4];
#pragma unroll
  for (int h = 0; h < 4; h++) {
    const int f = h == 0 ? 0 : h == 1 ? 3 : h == 2 ? 5 : 8, hf = h < 2 ? 2 : 7;
    const bool mine = (h & 1) ? t >= 2 : t < 2;
    qml[h] = mine ? qlo[hf] : 0u;
    qmh[h] = mine ? qhi[hf] : 0u;
    float a[4] = {0.f, 0.f, 0.f, 0.f}, c[4] = {0.f, 0.f, 0.f, 0.f};
    mma16816(a, qlo[f], qhi[f], qlo[f + 1], qhi[f + 1], klo[f], klo[f + 1]);
    mma16816(c, qlo[f], qhi[f], qlo[f + 1], qhi[f + 1], khi[f], khi[f + 1]);
    mma1688(a, qml[h], qmh[h], klo[hf]);
    mma1688(c, qml[h], qmh[h], khi[hf]);
    slo[h][0] = a[0];
    slo[h][1] = a[1];
    shi[h][0] = lg[h & 1][0] = far0 ? a[2] : c[2];
    shi[h][1] = lg[h & 1][1] = far1 ? a[3] : c[3];
    if (!ATT_MERGE && (h & 1)) softmax_two(lg, phi[h - 1], phi[h]);
  }
  TSIF(par == 0 && w == 1, 65);
  wg_sync(1 + par);
  TSIF(par == 0 && w == 1, 66);
  const bool nohist = (w == 0) && (b < 8);
  const uint4* hp = g_halo + ((b - 8) * 2 + par) * 224 + lane;
  uint32_t tg[7];
  if (w > 0) {
    const uint4 v0 = lds128(xa + (w - 1) * 2560), v1 = lds128(xa + (w - 1) * 2560 + 512), v2 = lds128(xa + (w - 1) * 2560 + 1024);
    const uint4 v3 = lds128(xa + (w - 1) * 2560 + 1536), v4 = lds128(xa + (w - 1) * 2560 + 2048);
    kpv[0] = v0.x; kpv[1] = v0.y; kpv[2] = v0.z; kpv[3] = v0.w; kpv[4] = v1.x; kpv[5] = v1.y; kpv[6] = v1.z; kpv[7] = v1.w;
    kpv[8] = v2.x; kpv[9] = v2.y; vpv[0] = v2.z; vpv[1] = v2.w; vpv[2] = v3.x; vpv[3] = v3.y; vpv[4] = v3.z; vpv[5] = v3.w;
    vpv[6] = v4.x; vpv[7] = v4.y; vpv[8] = v4.z; vpv[9] = v4.w;
  } else if (nohist) {
#pragma unroll
    for (int j = 0; j < 10; j++) kpv[j] = vpv[j] = 0u;
  } else {
    TSIF(par == 0, 77);
    halo_read(kpv, vpv, tg, hp);
  }
  if (w == 0 && !nohist) {
    int spins = 0;
    while (true) {
      bool ok = true;
#pragma unroll
      for (int j = 0; j < 7; j++) ok = ok && tg[j] == tag;
      if (__all_sync(0xffffffffu, ok) || ++spins > SPIN_LIMIT) break;
      halo_read(kpv, vpv, tg, hp);
    }
    TSIF(par == 0, 79);
  }
#pragma unroll
  for (int h = 0; h < 4; h++) {
    const int f = h == 0 ? 0 : h == 1 ? 3 : h == 2 ? 5 : 8, hf = h < 2 ? 2 : 7;
    float a[4] = {0.f, 0.f, 0.f, 0.f};
    mma16816(a, qlo[f], qhi[f], qlo[f + 1], qhi[f + 1], kpv[f], kpv[f + 1]);
    mma1688(a, qml[h], qmh[h], kpv[hf]);
    const float ninf = __int_as_float(0xff800000);
    lg[h & 1][0] = far0 ? (nohist ? ninf : a[0]) : slo[h][0];
    lg[h & 1][1] = far1 ? (nohist ? ninf : a[1]) : slo[h][1];
    if (h & 1) {
      softmax_two(lg, plo[h - 1], plo[h]);
      if (ATT_MERGE) {
        const float lh[2][2] = {{shi[h - 1][0], shi[h - 1][1]}, {shi[h][0], shi[h][1]}};
        softmax_two(lh, phi[h - 1], phi[h]);
      }
    }
  }
  TSIF(par == 0 && w <= 1, 67 + w);
  uint32_t ov[20];
#pragma unroll
  for (int hp = 0; hp < 2; hp++) {
    const int hf = hp ? 7 : 2;
    float sh[4] = {0.f, 0.f, 0.f, 0.f}, i0 = 0.f, i1 = 0.f;
#pragma unroll
    for (int e = 0; e < 2; e++) {
      const int h = 2 * hp + e, f = h == 0 ? 0 : h == 1 ? 3 : h == 2 ? 5 : 8;
      const uint32_t a0 = plo[h] & mfar, a2 = plo[h] & ~mfar, a3 = phi[h] & mfar, c1 = phi[h] & ~mfar;
      float sum[4] = {0.f, 0.f, 0.f, 0.f};
      mma1688(sum, plo[h], phi[h], 0x3F803F80u);
      const float r0 = rcp(sum[0]), r1 = rcp(sum[2]);
#pragma unroll
      for (int j = f; j < f + 2; j++) {
        float o[4] = {0.f, 0.f, 0.f, 0.f};
        mma16816(o, a0, 0u, a2, a3, vpv[j], vlo[j]);
        mma1688(o, 0u, c1, vhi[j]);
        ov[2 * j] = pack2(o[0] * r0, o[1] * r0);
        ov[2 * j + 1] = pack2(o[2] * r1, o[3] * r1);
      }
      const bool mine = e ? g >= 4 : g < 4;
      mma16816(sh, a0, 0u, a2, a3, mine ? vpv[hf] : 0u, mine ? vlo[hf] : 0u);
      mma1688(sh, 0u, c1, mine ? vhi[hf] : 0u);
      if (e == 0 || t >= 2) {
        i0 = r0;
        i1 = r1;
      }
    }
    ov[2 * hf] = pack2(sh[0] * i0, sh[1] * i0);
    ov[2 * hf + 1] = pack2(sh[2] * i1, sh[3] * i1);
  }
  TS(32 + 4 * par + w);
  mbar_wait(sb + OFF_BAR + 8 * B_P1, 0);
  const uint32_t oa = sb + OFF_OA + (lane >> 4) * 2048 + (32 * w + 2 * (lane & 15) + par) * 16;
#pragma unroll
  for (int j = 0; j < 5; j++) stsm4(oa + 4096 * j, ov + 4 * j);
  TSIF(par == 0 && w == 0, 120);
  fence_async_smem();
  TSIF(par == 0 && w == 0, 121);
  __syncwarp();
  if (lane == 0) mbar_arrive(sb + OFF_BAR + 8 * B_ATTN);
  TSM(w == 0 || w == 2, 122 + par + (w == 2 ? 3 : 0));
}

struct Maps {
  CUtensorMap x, wm, wt, k, v, y, wo, qm, qt, om, ot, u;
};

__device__ __forceinline__ void load_stage(uint32_t sb, int kb, int b, const Maps& m) {
  const uint32_t st = sb + (kb & 3) * STAGE_BYTES, bar = sb + OFF_BAR + 8 * (B_FULL1 + (kb & 3));
  const int r = b >> 3, hg = b & 7, slab = kb - KV_KB;
  const bool kv = slab >= 0 && slab < 5;
  const uint32_t kbar = sb + OFF_BAR + 8 * (B_KV + slab), dst = sb + OFF_KVS + slab * KVS_BYTES;
  mbar_expect_tx(bar, STAGE_BYTES);
  if (kv) mbar_expect_tx(kbar, KVS_BYTES);
  tma_3d(st, &m.x, 64 * kb, 64 * r, 0, bar);
  if (kv && KV_MIX) tma_3d(dst, &m.k, 0, 32 * (b >> 1) - 3, 2 * slab + (b & 1), kbar);
  tma_3d(st + ST_W, &m.wm, 80 * hg + (tail_first(hg) ? 16 : 0), 64 * kb, 0, bar);
  if (kv && KV_MIX) tma_3d(dst + KVS_V, &m.v, 0, 32 * (b >> 1), 2 * slab + (b & 1), kbar);
  tma_3d(st + ST_WT, &m.wt, 80 * hg + (tail_first(hg) ? 0 : 64), 64 * kb, 0, bar);
  if (kv && !KV_MIX) tma_3d(dst, &m.k, 0, 32 * (b >> 1) - 3, 2 * slab + (b & 1), kbar);
  if (kv && !KV_MIX) tma_3d(dst + KVS_V, &m.v, 0, 32 * (b >> 1), 2 * slab + (b & 1), kbar);
}

__global__ void __launch_bounds__(NTHR, 1) fused_kernel(const __grid_constant__ Maps m, const Params p) {
  extern __shared__ __align__(1024) uint8_t smem[];
  const uint32_t sb = (uint32_t)__cvta_generic_to_shared(smem);
  const uint32_t bars = sb + OFF_BAR;
  const int tid = threadIdx.x, lane = tid & 31;
  int b = blockIdx.x;
  if (BMAP == 1) b = (((b & 63) >> 3) * 2 + (b & 1)) * 8 + (((b < 64 ? 0x6521 : 0x7430) >> (4 * ((b >> 1) & 3))) & 7);
  if (BMAP == 2) b = ((b & 63) >> 2) * 8 + (((b < 64 ? 0x6521 : 0x7430) >> (4 * (b & 3))) & 7);
  if (BMAP == 3) b = (((b & 63) >> 3) * 2 + (b & 1)) * 8 + (((b < 64 ? 0x7430 : 0x6521) >> (4 * ((b >> 1) & 3))) & 7);
  if (BMAP == 4) b = (((b >> 4) * 2 + (b & 1)) * 8) + ((b >> 1) & 7);
  if (BMAP == 5) b = 127 - b;
  const int r = b >> 3, hg = b & 7;

  if (tid == T_ISSUE) {
    TSM(true, 0);
#pragma unroll
    for (int i = 0; i < 4; i++) mbar_init(bars + 8 * (B_FULL1 + i), 1);
#pragma unroll
    for (int i = 0; i < 3; i++) mbar_init(bars + 8 * (B_KV + i), 1);
    fence_async_smem();
#pragma unroll 1
    for (int kb = 0; kb <= PRE2; kb++) load_stage(sb, kb, b, m);
  } else if (tid >= T_PF && tid < T_PF + 12) {
    tm_prefetch(&m.x + (tid - T_PF));
  } else if (tid == T_INIT) {
#pragma unroll
    for (int i = 0; i < 4; i++) mbar_init(bars + 8 * (B_EMPTY1 + i), 8);
#pragma unroll
    for (int i = 0; i < 8; i++) mbar_init(bars + 8 * (B_FULL2 + i), 1);
#pragma unroll
    for (int i = 0; i < 4; i++) mbar_init(bars + 8 * (B_EMPTY2 + i), 8);
#pragma unroll
    for (int i = 0; i < 4; i++) mbar_init(bars + 8 * (B_U + i), 1);
    mbar_init(bars + 8 * B_HA, 4);
    mbar_init(bars + 8 * B_GATE, 4);
    mbar_init(bars + 8 * B_HB, 1);
    mbar_init(bars + 8 * B_KVD, 4);
    mbar_init(bars + 8 * B_QF, 1);
    mbar_init(bars + 8 * B_ATTN, 8);
    mbar_init(bars + 8 * B_P1, 8);
    mbar_init(bars + 8 * B_C34, 1);
#pragma unroll
    for (int i = 0; i < 5; i++) mbar_init(bars + 8 * (B_YST + i), 4);
#pragma unroll
    for (int i = 0; i < 5; i++) mbar_init(bars + 8 * (B_US + i), 4);
    mbar_init(bars + 8 * B_YSIG, 1);
    mbar_init(bars + 8 * B_YFULL, 1);
    mbar_init(bars + 8 * B_EPOCH, 1);
    mbar_init(bars + 8 * B_PREP, 4);
    mbar_init(bars + 8 * B_USIG, 1);
    mbar_init(bars + 8 * B_WST, 1);
#pragma unroll
    for (int i = 3; i < 5; i++) mbar_init(bars + 8 * (B_KV + i), 1);
    mbar_init(bars + 8 * B_E3, 8);
    mbar_init(bars + 8 * B_LAST, 1);
    mbar_init(bars + 8 * B_OSIG, 1);
    mbar_init(bars + 8 * B_WOP, 1);
    fence_async_smem();
  }
  const int warp = __shfl_sync(0xffffffffu, tid >> 5, 0), wg = warp >> 2, w = warp & 3;
  __syncthreads();

  if (wg == 3) {
    asm volatile("setmaxnreg.dec.sync.aligned.u32 56;");
    if (w == 0) {
      if (lane == 0) {
#pragma unroll 1
        for (int kb = 1 + PRE2; kb < 10; kb++) {
          if (kb >= 4) mbar_wait(bars + 8 * (kb == 7 ? B_E3 : B_EMPTY1 + (kb & 3)), (kb >> 3) & 1);
          TSIF(kb >= 4, 44 + kb);
          load_stage(sb, kb, b, m);
          TSIF(kb == 3, 60);
          if (kb == TRIG_KB) mbar_arrive(bars + 8 * B_LAST);
        }
        mbar_wait(bars + 8 * B_WOP, 0);
        mbar_wait(bars + 8 * WL_TRIG, 0);
        mbar_wait(bars + 8 * B_EPOCH, 0);
        flag_wait(g_cnt + C_W + 32 * hg, (lds32(sb + OFF_EPOCH) + 1) * 16);
        TS(30);
#pragma unroll 1
        for (int j = 0; j < 8; j++) {
          if (j >= 6) mbar_wait(bars + 8 * (B_EMPTY2 + j - 6), 0);
          if (j == 4) mbar_wait(bars + 8 * B_ATTN, 0);
          TSIF(j >= 6, 100 + j);
          if (RF_GATE && j == 6) mbar_wait(bars + 8 * B_YSIG, 0);
          mbar_expect_tx(bars + 8 * (B_FULL2 + j), j == 0 ? WO_BYTES : j == 5 ? O_BYTES + WO_BYTES + 512 : O_BYTES + WO_BYTES);
          bulk_load(sb + off_w(j), g_WO + (hg * 8 + step_src(hg, j)) * 800, WO_BYTES, bars + 8 * (B_FULL2 + j));
        }
        mbar_wait(bars + 8 * (B_EMPTY2 + 3), 0);
        mbar_expect_tx(bars + 8 * B_QF, O_BYTES);
        tma_2d(sb + OFF_QS, &m.qm, 80 * hg, 128 * r, bars + 8 * B_QF);
        tma_2d(sb + OFF_QT, &m.qt, 80 * hg + 64, 128 * r, bars + 8 * B_QF);
      }
    } else if (w == 1) {
      unsigned epoch = 0;
      if (lane == 0) {
        epoch = atomicAdd(g_cnt + C_LAUNCH, 1u) / NCTA;
        asm volatile("st.shared.u32 [%0], %1;" ::"r"(sb + OFF_EPOCH), "r"(epoch) : "memory");
        mbar_arrive(bars + 8 * B_EPOCH);
        mbar_wait(bars + 8 * B_KVD, 0);
        mbar_expect_tx(bars + 8 * B_HB, 5 * 4096);
#pragma unroll 1
        for (int c = 0; c < 5; c++) {
          if (c == 3) mbar_wait(bars + 8 * B_S3, 0);
          bulk_load(sb + off_ch(c) + U_BYTES, p.ssm_k + (5 * b + c) * SEQ, 4096, bars + 8 * B_HB);
        }
#pragma unroll
        for (int c = 0; c < 4; c++) mbar_expect_tx(bars + 8 * (B_U + c), c < 3 ? U_BYTES : 2 * U_BYTES);
        const uint4* usrc = g_U + 5 * b * U_PITCH;
        mbar_wait(bars + 8 * B_USIG, 0);
        flag_wait(g_cnt + C_PREP + 32 * (b & 15), (epoch + 1) * NCTA);
        TS(23);
#pragma unroll
        for (int c = 0; c < 5; c++) {
          if (c == 3) mbar_wait(bars + 8 * (B_U + 2), 0);
          bulk_load(sb + off_ch(c), usrc + c * U_PITCH, U_BYTES, bars + 8 * (B_U + (c < 3 ? c : 3)));
          TSIF(c == 0 || c == 4, 116 + (c >> 2));
        }
      }
      epoch = __shfl_sync(0xffffffffu, epoch, 0);
      if (lane < 8) {
        const int src = (b & ~7) | step_src(hg, lane);
        mbar_wait(bars + 8 * B_OSIG, 0);
        TS(20);
        flag_wait(g_cnt + C_O + 32 * src, epoch + 1);
        if (lane >= 1 && lane < 4) bulk_load(sb + off_o(lane), g_O + src * 1280, O_BYTES, bars + 8 * (B_FULL2 + lane));
        __syncwarp(0xff);
        TS(21);
        if (lane == 5) bulk_load(sb + OFF_GATE, g_gate + 128 * r, 512, bars + 8 * (B_FULL2 + 5));
#pragma unroll 1
        for (int j = 4; j < 8; j++) {
          if (lane == j) {
            mbar_wait(bars + 8 * (j < 6 ? B_C34 : B_EMPTY2 + j - 6), 0);
            if (RF_GATE && j == 6) mbar_wait(bars + 8 * B_YSIG, 0);
            bulk_load(sb + off_o(j), g_O + src * 1280, O_BYTES, bars + 8 * (B_FULL2 + j));
          }
          __syncwarp(0xff);
        }
        TS(22);
      }
    } else if (w == 2) {
      mbar_wait(bars + 8 * B_PREP, 0);
      flag_signal(g_cnt + C_PREP, 16, lane);
      TS(25);
      if (lane == 0) mbar_arrive(bars + 8 * B_USIG);
      mbar_wait(bars + 8 * B_GATE, 0);
      if (((NOMB & 1) || O_RB) && lane == 0) asm volatile("fence.release.gpu;" ::: "memory");
      mbar_wait(bars + 8 * B_ATTN, 0);
      if (lane == 0) {
        if (O_DEFER) mbar_wait(bars + 8 * (B_U + 3), 0);
        asm volatile("cp.async.bulk.global.shared::cta.bulk_group [%0], [%1], 20480;\ncp.async.bulk.commit_group;"
                     ::"l"(g_O + b * 1280), "r"(sb + OFF_OA) : "memory");
        if (O_RB) asm volatile("cp.async.bulk.wait_group.read 0;" ::: "memory");
        else asm volatile("cp.async.bulk.wait_group 0;\nfence.proxy.async.global;" ::: "memory");
      }
      TS(74);
      if (O_RB) {
        __syncwarp();
        unsigned v[5];
#pragma unroll
        for (int c = 0; c < 5; c++) v[c] = flag_read(reinterpret_cast<const unsigned*>(g_O + b * 1280 + 256 * c + 8 * lane + 7));
        const unsigned dep = __reduce_or_sync(0xffffffffu, (v[0] ^ v[1] ^ v[2] ^ v[3] ^ v[4]) & p.zero);
        if (lane == 0) flag_bump(g_cnt + C_O + 32 * b + dep);
      } else if (!(NOMB & 1)) flag_signal(g_cnt + C_O + 32 * b, 1, lane);
      else if (lane == 0) flag_bump(g_cnt + C_O + 32 * b);
      TS(26);
      if (lane == 0) mbar_arrive(bars + 8 * B_OSIG);

    } else {
      if (lane == 0) {
        uint4* dst = g_WO + (hg * 8 + (r >> 1)) * 800 + (r & 1) * 80;
        mbar_wait(bars + 8 * B_P1, 0);
        mbar_wait(bars + 8 * WB_TRIG, 0);
        mbar_expect_tx(bars + 8 * B_WST, WO_BYTES / 2);
        tma_3d(sb + OFF_WS, &m.wo, 0, 40 * r, 5 * hg, bars + 8 * B_WST);
        mbar_wait(bars + 8 * B_WST, 0);
        mbar_wait(bars + 8 * WO_TRIG, 0);
#pragma unroll 1
        for (int n = 0; n < 5; n++)
          asm volatile("cp.async.bulk.global.shared::cta.bulk_group [%0], [%1], 1280;" ::"l"(dst + 160 * n), "r"(sb + OFF_WS + 1280 * n) : "memory");
        asm volatile("cp.async.bulk.commit_group;\ncp.async.bulk.wait_group 0;\nfence.proxy.async.global;" ::: "memory");
        if (!(NOMB & 4)) asm volatile("fence.release.gpu;" ::: "memory");
        flag_bump(g_cnt + C_W + 32 * hg);
        mbar_arrive(bars + 8 * B_WOP);
        TS(71);
#pragma unroll 1
        for (int c = 0; c < 5; c++) {
          mbar_wait(bars + 8 * (B_YST + c), 0);
          asm volatile("cp.async.bulk.global.shared::cta.bulk_group [%0], [%1], 4096;\ncp.async.bulk.commit_group;"
                       ::"l"(g_Y + (5 * b + c) * Y_PITCH), "r"(sb + off_ch(c)) : "memory");
          if (c == 2) {
            asm volatile("cp.async.bulk.wait_group.read 0;" ::: "memory");
            mbar_arrive(bars + 8 * B_C34);
          }
        }
        if (Y_RB) asm volatile("cp.async.bulk.wait_group.read 0;" ::: "memory");
        else asm volatile("cp.async.bulk.wait_group 0;\nfence.proxy.async.global;" ::: "memory");
        TS(75);
      }
      unsigned dep = 0;
      if (Y_RB) {
        __syncwarp();
        unsigned v[5];
#pragma unroll
        for (int c = 0; c < 5; c++) v[c] = flag_read(reinterpret_cast<const unsigned*>(g_Y + (5 * b + c) * Y_PITCH + 8 * lane + 7));
        dep = __reduce_or_sync(0xffffffffu, (v[0] ^ v[1] ^ v[2] ^ v[3] ^ v[4]) & p.zero);
      }
      if (lane == 0) {
        if (!Y_RB && !(NOMB & 2)) asm volatile("fence.release.gpu;" ::: "memory");
        flag_bump(g_cnt + C_Y + 32 * (b >> 4) + dep);
        TS(27);
        mbar_arrive(bars + 8 * B_YSIG);
        mbar_expect_tx(bars + 8 * B_YFULL, 20480);
        flag_wait(g_cnt + C_Y + 32 * hg, (lds32(sb + OFF_EPOCH) + 1) * 16);
        TS(24);
        tma_2d(sb + OFF_YT, &m.y, 128 * r, 80 * hg, bars + 8 * B_YFULL);
        tma_2d(sb + OFF_YT + 10240, &m.y, 128 * r + 64, 80 * hg, bars + 8 * B_YFULL);
      }
    }
  } else {
    asm volatile("setmaxnreg.inc.sync.aligned.u32 152;");
    if (wg < 2) {
      float acc[120];
#pragma unroll
      for (int i = 0; i < 120; i++) acc[i] = 0.f;
      const uint32_t da = desc_lo(sb + wg * 8192, 16), db = desc_lo(sb + ST_W, 8192), dc = desc_lo(sb + ST_WT, 2048);
      if (PW1) pin<120>(acc);
      if (PW1 == 2) mbar_wait(bars + 8 * B_FULL1, 0);
#pragma unroll 1
      for (int kb = 0; kb < 10; kb++) {
        mbar_wait(bars + 8 * (B_FULL1 + (kb & 3)), (kb >> 2) & 1);
        const uint32_t so = (kb & 3) * (STAGE_BYTES >> 4);
        wg_fence();
#pragma unroll
        for (int k = 0; k < 4; k++) {
          WgSST<192>::mma<HI_SW128, HI_SW128>(acc, da + so + 2 * k, db + so + 128 * k, 1);
          WgSST<48>::mma<HI_SW128, HI_SW32>(acc + 96, da + so + 2 * k, dc + so + 32 * k, 1);
        }
        wg_commit();
        wg_wait<1>();
        if (kb > 0 && lane == 0) mbar_arrive(bars + 8 * (kb == 4 ? B_E3 : B_EMPTY1 + ((kb - 1) & 3)));
      }
      mbar_wait(bars + 8 * B_EPOCH, 0);
      const uint32_t tag = lds32(sb + OFF_EPOCH) + 1;
      mbar_wait(bars + 8 * B_S3, 0);
      wg_wait<0>();
      pin<120>(acc);
      if (lane == 0) mbar_arrive(bars + 8 * B_P1);
      TSM(w == 0, 3 + wg);
      attention(acc, sb, b, wg, w, lane, tag);
    } else {
      const int tw = tid & 127, chl = 64 * (b & 1) + 8 * w + (lane >> 2);
      uint4* up = g_U + chl * U_PITCH + ((4 * (b >> 1) + (lane & 3)) ^ ((b >> 2) & 1));
      uint2 sw[10];
      uint32_t dv = 0;
      if (lane < 5) dv = __ldg(reinterpret_cast<const unsigned short*>(p.ssm_D) + 5 * b + lane);
#pragma unroll
      for (int i = 0; i < 10; i++) sw[i] = ldg64(reinterpret_cast<const uint2*>(p.shift_k) + chl + 128 * (i >> 1) + 32 * (i & 1));
      uint32_t tab[12];
      uint32_t tt[2];
      fft_tables(tab, tw);
      fft_twiddles(tt, tw);
      uint4 res[10];
#pragma unroll
      for (int i = 0; i < 10; i++) res[i] = make_uint4(0, 0, 0, 0);
#pragma unroll 1
      for (int slab = 0; slab < 5; slab++) {
#pragma unroll
        for (int i = 0; i < 8; i++) res[i] = res[i + 2];
        prep_slab(res + 8, sw, sb, slab, w, lane);
        TSIF(w == 0, 99 + 4 * slab);
#pragma unroll
        for (int i = 0; i < 8; i++) sw[i] = sw[i + 2];
      }
      TSIF(w == 0, 28);
      __syncwarp();
      if (lane == 0) mbar_arrive(bars + 8 * B_KVD + ((res[8].x ^ res[9].x) & p.zero));
      mbar_wait(bars + 8 * B_KVD, 0);
      fft_tables_store(tab, sb, tw);
      mbar_wait(bars + 8 * B_LAST, 0);
#pragma unroll
      for (int i = 0; i < 10; i++) up[(128 * (i >> 1) + 32 * (i & 1)) * U_PITCH] = res[i];
      __syncwarp();
      if (lane == 0) mbar_arrive(bars + 8 * B_PREP);
      TSIF(w == 0 && !U_TMA, 5);
      mbar_wait(bars + 8 * (G_AFTER ? B_USIG : B_LAST), 0);
      prep_gate(p, b, w, lane);
      __syncwarp();
      if (lane == 0) mbar_arrive(bars + 8 * B_GATE);
      TSIF(w == 0, 72);
      mbar_wait(bars + 8 * B_HB, 0);
      TSIF(w == 0, 2);
      const uint32_t ha = sb + U_BYTES + ((tw >> 3) * 16 + 8 + (tw & 7)) * 16;
      uint4 hv[5];
#pragma unroll
      for (int c = 0; c < 5; c++) hv[c] = lds128(ha + off_ch(c));
      __syncwarp();
#pragma unroll
      for (int c = 0; c < 5; c++) sts128((ha ^ 16) + off_ch(c), hv[c].x, hv[c].y, hv[c].z, hv[c].w);
      asm volatile("st.shared.v2.u32 [%0], {%1, %2};" ::"r"(sb + OFF_TT + 8 * tw), "r"(tt[0]), "r"(tt[1]) : "memory");
      if (tw < 5) asm volatile("st.shared.f32 [%0], %1;" ::"r"(sb + OFF_D + 4 * tw), "f"(bf_lo(dv) * 0.125f) : "memory");
      fence_async_smem();
      __syncwarp();
      if (lane == 0) mbar_arrive(bars + 8 * B_HA);
      TSIF(w == 0, 6);
    }

    FftConst fc;
    TSM(w == 0 && wg == 0, 104);
    mbar_wait(bars + 8 * B_HA, 0);
    fft_matrices(fc, sb, w, lane);
    TSM(w == 0 && wg == 0, 105);
    if (ATT_GATE && !H_EARLY) mbar_wait(bars + 8 * B_ATTN, 0);
    TSM(w == 0 && wg == 2, 124);
#pragma unroll 1
    for (uint32_t tasks = wg == 0 ? TASK0 : wg == 1 ? TASK1 : TASK2; tasks; tasks >>= 4) {
      const int c = (tasks & 7) - 1;
      conv_channel(fc, sb, c, wg, w, lane);
      if (lane == 0) mbar_arrive(bars + 8 * (B_YST + c));
      TSM(w == 0, 10 + c);
    }

    if (wg < 2) {
      const int g = lane >> 2;
      float acc[40];
#pragma unroll
      for (int i = 0; i < 40; i++) acc[i] = 0.f;
      const uint32_t da = desc_lo(sb + wg * 1024, 2048), db = desc_lo(sb, 2560);
      mbar_wait(bars + 8 * B_ATTN, 0);
      mbar_wait(bars + 8 * (B_YST + 3), 0);
      mbar_wait(bars + 8 * (B_YST + 4), 0);
      if (PW2) mbar_wait(bars + 8 * B_FULL2, 0);
      TSM(w == 0, 15 + wg);
#pragma unroll 1
      for (int j = 0; j < 8; j++) {
        mbar_wait(bars + 8 * (B_FULL2 + j), 0);
        const uint32_t oa = da + (off_o(j) >> 4), ob = db + (off_w(j) >> 4);
        wg_fence();
#pragma unroll
        for (int k = 0; k < 5; k++) WgSST<80>::mma<HI_NONE, HI_SW32>(acc, oa + 256 * k, ob + 32 * k, 1);
        wg_commit();
        wg_wait<1>();
        if (j >= 1 && j <= 4 && lane == 0) mbar_arrive(bars + 8 * (B_EMPTY2 + j - 1));
      }
      TSIF(w == 0 && wg == 0, 113);
      const int tr = 64 * wg + 16 * w + (lane & 15);
      const uint32_t fm = sb + OFF_QS + tr * 128, fx = (lane >> 4) ^ (tr & 7);
      const uint32_t ft = sb + OFF_QT + tr * 32 + (((lane >> 4) ^ (tr >> 2)) & 1) * 16;
      const float g0 = __uint_as_float(lds32(sb + OFF_GATE + (64 * wg + 16 * w + g) * 4));
      const float g1 = __uint_as_float(lds32(sb + OFF_GATE + (64 * wg + 16 * w + 8 + g) * 4));
      const uint32_t ga = pack2(g0, g0), gb = pack2(g1, g1);
      const uint32_t na = pack2(1.f - g0, 1.f - g0), nb = pack2(1.f - g1, 1.f - g1);

      wg_wait<0>();
      pin<40>(acc);
      TSM(w == 0, 17 + wg);
      uint32_t pb[20];
#pragma unroll
      for (int j = 0; j < 10; j++) {
        pb[2 * j] = bmul(na, pack2(acc[4 * j], acc[4 * j + 1]));
        pb[2 * j + 1] = bmul(nb, pack2(acc[4 * j + 2], acc[4 * j + 3]));
        asm volatile("" : "+r"(pb[2 * j]), "+r"(pb[2 * j + 1]));
      }
      const uint32_t ya = sb + OFF_YT + wg * 10240 + ((lane >> 4) * 8 + (lane & 7)) * 128 +
                          (((2 * w + (((lane >> 3) & 1) ^ wg)) ^ (lane & 7)) << 4);
      uint32_t qf[20];
      mbar_wait(bars + 8 * B_QF, 0);
#pragma unroll
      for (int j = 0; j < 5; j++) ldsm4(qf + 4 * j, j < 4 ? fm + ((fx ^ (2 * j)) << 4) : ft);
      mbar_wait(bars + 8 * B_YFULL, 0);
      TSM(w == 0 && wg == 0, 19);
#pragma unroll
      for (int j = 0; j < 5; j++) {
        uint32_t y[4];
        ldsm4t(y, ya + 2048 * j);
#pragma unroll
        for (int i = 0; i < 4; i++) qf[4 * j + i] = badd(bmul((i & 1) ? gb : ga, bmul(qf[4 * j + i], y[i])), pb[4 * j + i]);
      }
#pragma unroll
      for (int j = 0; j < 5; j++) stsm4(j < 4 ? fm + ((fx ^ (2 * j)) << 4) : ft, qf + 4 * j);
      fence_async_smem();
      __syncwarp();
      if (lane == 0) {
        const int row = 64 * wg + 16 * w;
        asm volatile("cp.async.bulk.tensor.2d.global.shared::cta.bulk_group [%0, {%2, %3}], [%1];"
                     ::"l"(&m.om), "r"(sb + OFF_QS + row * 128), "r"(80 * hg), "r"(128 * r + row) : "memory");
        asm volatile("cp.async.bulk.tensor.2d.global.shared::cta.bulk_group [%0, {%2, %3}], [%1];"
                     ::"l"(&m.ot), "r"(sb + OFF_QT + row * 32), "r"(80 * hg + 64), "r"(128 * r + row) : "memory");
        asm volatile("cp.async.bulk.commit_group;\ncp.async.bulk.wait_group.read 0;" ::: "memory");
      }
      TSM(true, 40 + 4 * wg + w);
      if (ENDBAR) asm volatile("bar.sync 15, 256;" ::: "memory");
    }
  }
}

typedef CUresult (*EncodeFn)(CUtensorMap*, CUtensorMapDataType, cuuint32_t, void*, const cuuint64_t*, const cuuint64_t*,
                             const cuuint32_t*, const cuuint32_t*, CUtensorMapInterleave, CUtensorMapSwizzle,
                             CUtensorMapL2promotion, CUtensorMapFloatOOBfill);

void encode(EncodeFn fn, CUtensorMap* tm, const void* base, int rank, const cuuint64_t* dims, const cuuint64_t* strides,
            const cuuint32_t* box, CUtensorMapSwizzle swz) {
  const cuuint32_t ones[3] = {1, 1, 1};
  fn(tm, CU_TENSOR_MAP_DATA_TYPE_BFLOAT16, rank, const_cast<void*>(base), dims, strides, box, ones,
     CU_TENSOR_MAP_INTERLEAVE_NONE, swz, CU_TENSOR_MAP_L2_PROMOTION_L2_128B, CU_TENSOR_MAP_FLOAT_OOB_FILL_NONE);
}

}

extern "C" void kernel_launch(void* const* d_in, const int* in_sizes, int n_in, void* d_out, int out_size) {
  (void)in_sizes; (void)n_in; (void)out_size;
  Params p;
  p.q = (const __nv_bfloat16*)d_in[0];
  p.k = (const __nv_bfloat16*)d_in[1];
  p.v = (const __nv_bfloat16*)d_in[2];
  p.shift_k = (const __nv_bfloat16*)d_in[3];
  p.ssm_k = (const __nv_bfloat16*)d_in[4];
  p.ssm_D = (const __nv_bfloat16*)d_in[5];
  p.wqkv = (const __nv_bfloat16*)d_in[7];
  p.wo = (const __nv_bfloat16*)d_in[8];
  p.gate_w = (const __nv_bfloat16*)d_in[9];
  p.out = (__nv_bfloat16*)d_out;
  p.zero = 0;

  static EncodeFn fn = nullptr;
  static void *yaddr = nullptr, *uaddr = nullptr;
  if (!fn) {
    cudaDriverEntryPointQueryResult qr;
    void* f = nullptr;
    cudaGetDriverEntryPoint("cuTensorMapEncodeTiled", &f, cudaEnableDefault, &qr);
    fn = (EncodeFn)f;
    cudaGetSymbolAddress(&yaddr, g_Y);
    cudaGetSymbolAddress(&uaddr, g_U);
    cudaFuncSetAttribute(fused_kernel, cudaFuncAttributeMaxDynamicSharedMemorySize, SMEM_BYTES);
  }
  Maps m;
  {
    const cuuint64_t dims[3] = {640, 1024, 2}, st[2] = {2560, 1280};
    const cuuint32_t box[3] = {64, 64, 2};
    encode(fn, &m.x, p.q, 3, dims, st, box, CU_TENSOR_MAP_SWIZZLE_128B);
  }
  {
    const cuuint64_t dims[3] = {640, 640, 3}, st[2] = {3840, 1280};
    const cuuint32_t box[3] = {64, 64, 3}, boxt[3] = {16, 64, 3};
    encode(fn, &m.wm, p.wqkv, 3, dims, st, box, CU_TENSOR_MAP_SWIZZLE_128B);
    encode(fn, &m.wt, p.wqkv, 3, dims, st, boxt, CU_TENSOR_MAP_SWIZZLE_32B);
  }
  {
    const cuuint64_t dims[3] = {64, 2048, 10}, st[2] = {1280, 128};
    const cuuint32_t boxk[3] = {64, 35, 1}, boxv[3] = {64, 32, 1};
    encode(fn, &m.k, p.k, 3, dims, st, boxk, CU_TENSOR_MAP_SWIZZLE_128B);
    encode(fn, &m.v, p.v, 3, dims, st, boxv, CU_TENSOR_MAP_SWIZZLE_128B);
  }
  {
    const cuuint64_t dims[3] = {16, 640, 40}, st[2] = {1280, 32};
    const cuuint32_t box[3] = {16, 40, 5};
    encode(fn, &m.wo, p.wo, 3, dims, st, box, CU_TENSOR_MAP_SWIZZLE_32B);
  }
  {
    const cuuint64_t dims[2] = {2048, 640}, st[1] = {Y_PITCH * 16};
    const cuuint32_t box[2] = {64, 80};
    encode(fn, &m.y, yaddr, 2, dims, st, box, CU_TENSOR_MAP_SWIZZLE_128B);
    const cuuint64_t stu[1] = {U_PITCH * 16};
    const cuuint32_t boxu[2] = {32, 64};
    encode(fn, &m.u, uaddr, 2, dims, stu, boxu, CU_TENSOR_MAP_SWIZZLE_NONE);
  }
  {
    const cuuint64_t dims[2] = {640, 2048}, st[1] = {1280};
    const cuuint32_t bqm[2] = {64, 128}, bqt[2] = {16, 128}, bom[2] = {64, 16}, bot[2] = {16, 16};
    encode(fn, &m.qm, p.q, 2, dims, st, bqm, CU_TENSOR_MAP_SWIZZLE_128B);
    encode(fn, &m.qt, p.q, 2, dims, st, bqt, CU_TENSOR_MAP_SWIZZLE_32B);
    encode(fn, &m.om, p.out, 2, dims, st, bom, CU_TENSOR_MAP_SWIZZLE_128B);
    encode(fn, &m.ot, p.out, 2, dims, st, bot, CU_TENSOR_MAP_SWIZZLE_32B);
  }
  fused_kernel<<<NCTA, NTHR, SMEM_BYTES>>>(m, p);
}
```

```cpp
#include <cuda.h>
#include <cuda_bf16.h>
#include <cuda_runtime.h>
#include <stdint.h>

namespace {

constexpr int SEQ = 2048, DIM = 640, NCTA = 128, NTHR = 512;

#define TRIG_KB 9
#define KV_KB 2
#define DEV_EXIT 0
#define ATT_GATE 0
#define G_AFTER 0
#define FENCE_LO 0
#define FENCE_HI 0
#define PW1 2
#define PW2 1
#define ENDBAR 0
#define PAD_KB 0
#define Y_ALIAS 1
#define H_EARLY 1
#define NOMB 0
#define SRC_ROT 2
#define WAIT_NS 0
#define WB_TRIG B_USIG
#define G_POS 0
#define TAILF 1
#define T_ISSUE 384
#define T_PF 416
#define T_INIT 448
#define ATT_MERGE 0
#define BMAP 1
#define PRE2 1
#define KV_MIX 0
#define O_DEFER 0
#define TASK0 0x52
#define TASK1 0x3
#define TASK2 0x41
#define HALO_FIRST 1
#define PREV_EARLY 0
#define Y_RB 0
#define O_RB 0
#define O_EAGER 1
#define OP_TRIG B_OSIG
#define ACQ 0
#define U_TMA 0
#define U_GATE 0
#define RF_GATE 0
#define WO_TRIG B_WST
#define WL_TRIG B_WOP
#define WO_GATE 1

constexpr uint32_t STAGE_BYTES = 47104, ST_W = 16384, ST_WT = 40960;
constexpr uint32_t O_BYTES = 20480, WO_BYTES = 12800;
constexpr uint32_t OFF_OA = 0;
constexpr uint32_t OFF_QS = 3 * O_BYTES, OFF_QT = OFF_QS + 16384;
constexpr uint32_t OFF_WC = 81920;
constexpr uint32_t OFF_WA = 94720;
constexpr uint32_t OFF_GATE = 145920;
constexpr uint32_t OFF_TT = 146432;
constexpr uint32_t OFF_KVX = 148480;
constexpr uint32_t OFF_CH3 = 163840;
constexpr uint32_t CH_BYTES = 12288, U_BYTES = 4096;
constexpr uint32_t OFF_FT = 225280, OFF_GT = 229376;
constexpr uint32_t OFF_CH0 = 188416;
constexpr uint32_t OFF_KVS = OFF_CH0, KVS_V = 4480, KVS_BYTES = 8576;
constexpr uint32_t OFF_WS = OFF_WA;
__device__ __forceinline__ uint32_t off_us(int s) { return OFF_CH0 + 4096 * ((0x65320 >> (4 * s)) & 7); }
constexpr uint32_t OFF_YT = 163840;
constexpr uint32_t OFF_BAR = 231936;
constexpr uint32_t SMEM_BYTES = OFF_BAR + 512;

enum : uint32_t {
  B_FULL1 = 0, B_EMPTY1 = 4, B_S3 = 7, B_FULL2 = 52, B_EMPTY2 = 13, B_U = 8, B_GATE = 12, B_HA = 19, B_HB = 20,
  B_ATTN = 21, B_C34 = 22, B_CONV = 23, B_YFULL = 24, B_EPOCH = 25, B_PREP = 26, B_P1 = 27, B_LAST = 28,
  B_E3 = 29, B_OSIG = 30, B_WOP = 31, B_USIG = 32, B_WST = 33, B_KV = 34, B_KVD = 39, B_QF = 17, B_YST = 40,
  B_US = 45, B_YSIG = 50
};
constexpr uint32_t OFF_EPOCH = OFF_BAR + 8 * 51, OFF_D = OFF_BAR + 8 * 60;
__device__ __forceinline__ uint32_t off_o(int j) { return j < 4 ? OFF_OA + j * O_BYTES : j < 6 ? OFF_CH0 + (j - 4) * O_BYTES : OFF_OA + (j - 6) * O_BYTES; }
__device__ __forceinline__ uint32_t off_w(int j) { return j < 4 ? OFF_WA + j * WO_BYTES : j == 4 ? OFF_KVX : j == 5 ? OFF_WC : OFF_WA + (j - 6) * WO_BYTES; }
__device__ __forceinline__ int step_src(int hg, int j) {
  if (SRC_ROT == 2) {
    const int pos = (0x37621540 >> (4 * hg)) & 7;
    return j == 0 ? hg : (0x65217430 >> (4 * (j <= pos ? j - 1 : j))) & 7;
  }
  return SRC_ROT ? (hg + j) & 7 : j == 0 ? hg : j <= hg ? j - 1 : j;
}
__device__ __forceinline__ bool tail_first(int hg) { return TAILF && (hg & 3) == 3; }
__device__ __forceinline__ uint32_t off_ch(int c) { return (c < 3 ? OFF_CH0 : OFF_CH3 - 3 * CH_BYTES) + c * CH_BYTES; }

#define U_PITCH 264
__device__ __align__(1024) uint4 g_U[DIM * U_PITCH];
__device__ uint4 g_O[NCTA * 1280];
#define g_Y g_U
constexpr int Y_PITCH = U_PITCH;
__device__ uint4 g_WO[64 * 800];
__device__ uint4 g_halo[NCTA * 2 * 7 * 32];
__device__ float g_gate[SEQ + PAD_KB * 256];
__device__ unsigned g_cnt[32 * (1 + 2 * 16 + 8 + NCTA)];
constexpr int C_LAUNCH = 0, C_PREP = 32, C_Y = 32 * 17, C_W = 32 * 33, C_O = 32 * 41;

#define TSM(cond, slot) do { } while (0)
#define TSIF(cond, slot) do { if (__LINE__ >= FENCE_LO && __LINE__ < FENCE_HI) sched_fence(); } while (0)
__device__ __forceinline__ void sched_fence() {
  asm volatile("{\n.reg .pred p;\n.reg .u32 c;\nmov.u32 c, %%clock;\nsetp.eq.u32 p, c, 0;\n@p st.shared.u32 [%0], c;\n}"
               ::"r"(1024 + OFF_EPOCH + 4) : "memory");
}
#define TS(slot) TSIF(true, slot)

struct Params {
  const __nv_bfloat16 *q, *k, *v, *shift_k, *ssm_k, *ssm_D, *wqkv, *wo, *gate_w;
  __nv_bfloat16* out;
  uint32_t zero;
};

#define POLL_NS 0
constexpr int SPIN_LIMIT = 1 << 17;

__device__ __forceinline__ void mbar_init(uint32_t bar, uint32_t count) {
  asm volatile("mbarrier.init.shared::cta.b64 [%0], %1;" ::"r"(bar), "r"(count) : "memory");
}
__device__ __forceinline__ void mbar_expect_tx(uint32_t bar, uint32_t bytes) {
  asm volatile("mbarrier.arrive.expect_tx.shared::cta.b64 _, [%0], %1;" ::"r"(bar), "r"(bytes) : "memory");
}
__device__ __forceinline__ void mbar_arrive(uint32_t bar) {
  asm volatile("mbarrier.arrive.shared::cta.b64 _, [%0];" ::"r"(bar) : "memory");
}
__device__ __forceinline__ void mbar_wait(uint32_t bar, uint32_t parity) {
  uint32_t ok;
  int spins = 0;
  do {
    if (WAIT_NS)
      asm volatile("{\n.reg .pred p;\nmbarrier.try_wait.parity.shared::cta.b64 p, [%1], %2, %3;\nselp.b32 %0, 1, 0, p;\n}"
                   : "=r"(ok) : "r"(bar), "r"(parity), "r"(WAIT_NS) : "memory");
    else
      asm volatile("{\n.reg .pred p;\nmbarrier.try_wait.parity.shared::cta.b64 p, [%1], %2;\nselp.b32 %0, 1, 0, p;\n}"
                   : "=r"(ok) : "r"(bar), "r"(parity) : "memory");
    if (++spins > SPIN_LIMIT) break;
  } while (!ok);
}
__device__ __forceinline__ unsigned flag_read(const unsigned* p) {
  unsigned v;
  asm volatile("ld.relaxed.gpu.global.u32 %0, [%1];" : "=r"(v) : "l"(p) : "memory");
  return v;
}
__device__ __forceinline__ void flag_poll(const unsigned* p, unsigned target) {
  unsigned v;
  int spins = 0;
  do {
    if (POLL_NS && spins) __nanosleep(POLL_NS);
    asm volatile("ld.relaxed.gpu.global.u32 %0, [%1];" : "=r"(v) : "l"(p) : "memory");
    if (++spins > SPIN_LIMIT) break;
  } while ((int)(v - target) < 0);
}
__device__ __forceinline__ void flag_wait(const unsigned* p, unsigned target) {
  flag_poll(p, target);
  if (ACQ) asm volatile("fence.acquire.gpu;\nfence.proxy.async.global;" ::: "memory");
}
__device__ __forceinline__ void flag_signal(unsigned* p, int n, int lane) {
  if (lane == 0) asm volatile("fence.release.gpu;" ::: "memory");
  __syncwarp();
  if (lane < n) asm volatile("red.relaxed.gpu.global.add.u32 [%0], 1;" ::"l"(p + 32 * lane) : "memory");
}
__device__ __forceinline__ void flag_bump(unsigned* p) {
  asm volatile("red.relaxed.gpu.global.add.u32 [%0], 1;" ::"l"(p) : "memory");
}
__device__ __forceinline__ void fence_async_smem() { asm volatile("fence.proxy.async.shared::cta;" ::: "memory"); }
__device__ __forceinline__ void wg_sync(int id) { asm volatile("bar.sync %0, 128;" ::"r"(id) : "memory"); }

__device__ __forceinline__ void tma_2d(uint32_t dst, const CUtensorMap* tm, int c0, int c1, uint32_t bar) {
  asm volatile("cp.async.bulk.tensor.2d.shared::cluster.global.mbarrier::complete_tx::bytes [%0], [%1, {%3, %4}], [%2];"
               ::"r"(dst), "l"(tm), "r"(bar), "r"(c0), "r"(c1) : "memory");
}
__device__ __forceinline__ void tma_3d(uint32_t dst, const CUtensorMap* tm, int c0, int c1, int c2, uint32_t bar) {
  asm volatile("cp.async.bulk.tensor.3d.shared::cluster.global.mbarrier::complete_tx::bytes [%0], [%1, {%3, %4, %5}], [%2];"
               ::"r"(dst), "l"(tm), "r"(bar), "r"(c0), "r"(c1), "r"(c2) : "memory");
}
__device__ __forceinline__ void bulk_load(uint32_t dst, const void* src, uint32_t bytes, uint32_t bar) {
  asm volatile("cp.async.bulk.shared::cluster.global.mbarrier::complete_tx::bytes [%0], [%1], %2, [%3];"
               ::"r"(dst), "l"(src), "r"(bytes), "r"(bar) : "memory");
}
__device__ __forceinline__ void tm_prefetch(const CUtensorMap* tm) {
  asm volatile("prefetch.tensormap [%0];" ::"l"(tm) : "memory");
}

__device__ __forceinline__ void wg_fence() { asm volatile("wgmma.fence.sync.aligned;" ::: "memory"); }
__device__ __forceinline__ void wg_commit() { asm volatile("wgmma.commit_group.sync.aligned;" ::: "memory"); }
template <int N> __device__ __forceinline__ void wg_wait() { asm volatile("wgmma.wait_group.sync.aligned %0;" ::"n"(N) : "memory"); }
__device__ __forceinline__ uint32_t desc_lo(uint32_t addr, uint32_t lbo) { return ((addr & 0x3FFFF) >> 4) | ((lbo >> 4) << 16); }
constexpr uint32_t desc_hi(uint32_t sbo, uint32_t swz) { return (sbo >> 4) | (swz << 30); }
constexpr uint32_t HI_SW128 = desc_hi(1024, 1), HI_SW64 = desc_hi(512, 2), HI_SW32 = desc_hi(256, 3), HI_NONE = desc_hi(128, 0);
template <int N> __device__ __forceinline__ void pin(float* d) {
#pragma unroll
  for (int i = 0; i < N; i++) asm volatile("" : "+f"(d[i])::"memory");
}

__device__ __forceinline__ uint32_t lds32(uint32_t a) {
  uint32_t v;
  asm volatile("ld.volatile.shared.u32 %0, [%1];" : "=r"(v) : "r"(a) : "memory");
  return v;
}
__device__ __forceinline__ uint4 ldg128(const void* a) {
  uint4 v;
  asm volatile("ld.global.nc.v4.u32 {%0, %1, %2, %3}, [%4];" : "=r"(v.x), "=r"(v.y), "=r"(v.z), "=r"(v.w) : "l"(a) : "memory");
  return v;
}
__device__ __forceinline__ uint2 ldg64(const void* a) {
  uint2 v;
  asm volatile("ld.global.nc.v2.u32 {%0, %1}, [%2];" : "=r"(v.x), "=r"(v.y) : "l"(a) : "memory");
  return v;
}
__device__ __forceinline__ void ldsm4(uint32_t* r, uint32_t a) {
  asm volatile("ldmatrix.sync.aligned.m8n8.x4.shared.b16 {%0, %1, %2, %3}, [%4];"
               : "=r"(r[0]), "=r"(r[1]), "=r"(r[2]), "=r"(r[3]) : "r"(a) : "memory");
}
__device__ __forceinline__ void ldsm4t(uint32_t* r, uint32_t a) {
  asm volatile("ldmatrix.sync.aligned.m8n8.x4.trans.shared.b16 {%0, %1, %2, %3}, [%4];"
               : "=r"(r[0]), "=r"(r[1]), "=r"(r[2]), "=r"(r[3]) : "r"(a) : "memory");
}
__device__ __forceinline__ uint2 lds64(uint32_t a) {
  uint2 v;
  asm volatile("ld.shared.v2.u32 {%0, %1}, [%2];" : "=r"(v.x), "=r"(v.y) : "r"(a) : "memory");
  return v;
}
__device__ __forceinline__ uint4 lds128(uint32_t a) {
  uint4 v;
  asm volatile("ld.shared.v4.u32 {%0, %1, %2, %3}, [%4];" : "=r"(v.x), "=r"(v.y), "=r"(v.z), "=r"(v.w) : "r"(a) : "memory");
  return v;
}
__device__ __forceinline__ void sts128(uint32_t a, uint32_t x, uint32_t y, uint32_t z, uint32_t w) {
  asm volatile("st.shared.v4.u32 [%0], {%1, %2, %3, %4};" ::"r"(a), "r"(x), "r"(y), "r"(z), "r"(w) : "memory");
}
__device__ __forceinline__ void stsm4(uint32_t a, const uint32_t* r) {
  asm volatile("stmatrix.sync.aligned.m8n8.x4.shared.b16 [%0], {%1, %2, %3, %4};" ::"r"(a), "r"(r[0]), "r"(r[1]), "r"(r[2]), "r"(r[3]) : "memory");
}
__device__ __forceinline__ void stsm4t(uint32_t a, const uint32_t* r) {
  asm volatile("stmatrix.sync.aligned.m8n8.x4.trans.shared.b16 [%0], {%1, %2, %3, %4};" ::"r"(a), "r"(r[0]), "r"(r[1]), "r"(r[2]), "r"(r[3]) : "memory");
}
__device__ __forceinline__ uint32_t pack2(float lo, float hi) {
  uint32_t r;
  asm("cvt.rn.bf16x2.f32 %0, %1, %2;" : "=r"(r) : "f"(hi), "f"(lo));
  return r;
}
__device__ __forceinline__ uint32_t movm(uint32_t a) {
  uint32_t d;
  asm volatile("movmatrix.sync.aligned.m8n8.trans.b16 %0, %1;" : "=r"(d) : "r"(a));
  return d;
}
__device__ __forceinline__ uint32_t bmul(uint32_t a, uint32_t b) {
  uint32_t d;
  asm("mul.rn.bf16x2 %0, %1, %2;" : "=r"(d) : "r"(a), "r"(b));
  return d;
}
__device__ __forceinline__ uint32_t badd(uint32_t a, uint32_t b) {
  uint32_t d;
  asm("add.rn.bf16x2 %0, %1, %2;" : "=r"(d) : "r"(a), "r"(b));
  return d;
}
__device__ __forceinline__ uint32_t bfma(uint32_t a, uint32_t b, uint32_t c) {
  uint32_t d;
  asm("fma.rn.bf16x2 %0, %1, %2, %3;" : "=r"(d) : "r"(a), "r"(b), "r"(c));
  return d;
}
__device__ __forceinline__ float bf_lo(uint32_t x) { return __uint_as_float(x << 16); }
__device__ __forceinline__ float bf_hi(uint32_t x) { return __uint_as_float(x & 0xFFFF0000u); }
__device__ __forceinline__ float ex2(float x) {
  float y;
  asm("ex2.approx.ftz.f32 %0, %1;" : "=f"(y) : "f"(x));
  return y;
}
__device__ __forceinline__ float rcp(float x) {
  float y;
  asm("rcp.approx.ftz.f32 %0, %1;" : "=f"(y) : "f"(x));
  return y;
}
__device__ __forceinline__ void mma16816(float* d, uint32_t a0, uint32_t a1, uint32_t a2, uint32_t a3, uint32_t b0, uint32_t b1) {
  asm volatile("mma.sync.aligned.m16n8k16.row.col.f32.bf16.bf16.f32 {%0, %1, %2, %3}, {%4, %5, %6, %7}, {%8, %9}, {%0, %1, %2, %3};"
               : "+f"(d[0]), "+f"(d[1]), "+f"(d[2]), "+f"(d[3])
               : "r"(a0), "r"(a1), "r"(a2), "r"(a3), "r"(b0), "r"(b1));
}
__device__ __forceinline__ void mma1688(float* d, uint32_t a0, uint32_t a1, uint32_t b0) {
  asm volatile("mma.sync.aligned.m16n8k8.row.col.f32.bf16.bf16.f32 {%0, %1, %2, %3}, {%4, %5}, {%6}, {%0, %1, %2, %3};"
               : "+f"(d[0]), "+f"(d[1]), "+f"(d[2]), "+f"(d[3])
               : "r"(a0), "r"(a1), "r"(b0));
}

template <int N> struct WgRS;
template <int N> struct WgSST;
template <> struct WgRS<32> {
  template <uint32_t HB>
  static __device__ __forceinline__ void mma(float* d, const uint32_t* a, uint32_t db) {
    asm volatile("{\n.reg .pred p;\n.reg .b64 db;\nsetp.ne.b32 p, %22, 0;\n"
      "mov.b64 db, {%20, %21};\n"
      "wgmma.mma_async.sync.aligned.m64n32k16.f32.bf16.bf16 {"
      "%0, %1, %2, %3, %4, %5, %6, %7, %8, %9, %10, %11, %12, %13, %14, %15"
      "}, {%16, %17, %18, %19}, db, p, 1, 1, 1;\n}\n"
      : "+f"(d[0]), "+f"(d[1]), "+f"(d[2]), "+f"(d[3]), "+f"(d[4]), "+f"(d[5]), "+f"(d[6]), "+f"(d[7]),
        "+f"(d[8]), "+f"(d[9]), "+f"(d[10]), "+f"(d[11]), "+f"(d[12]), "+f"(d[13]), "+f"(d[14]), "+f"(d[15])
      : "r"(a[0]), "r"(a[1]), "r"(a[2]), "r"(a[3]), "r"(db), "n"(HB), "n"(1));
  }
  template <uint32_t HB>
  static __device__ __forceinline__ void set(float* d, const uint32_t* a, uint32_t db) {
    asm volatile("{\n.reg .pred p;\n.reg .b64 db;\nsetp.ne.b32 p, %22, 0;\n"
      "mov.b64 db, {%20, %21};\n"
      "wgmma.mma_async.sync.aligned.m64n32k16.f32.bf16.bf16 {"
      "%0, %1, %2, %3, %4, %5, %6, %7, %8, %9, %10, %11, %12, %13, %14, %15"
      "}, {%16, %17, %18, %19}, db, p, 1, 1, 1;\n}\n"
      : "=f"(d[0]), "=f"(d[1]), "=f"(d[2]), "=f"(d[3]), "=f"(d[4]), "=f"(d[5]), "=f"(d[6]), "=f"(d[7]),
        "=f"(d[8]), "=f"(d[9]), "=f"(d[10]), "=f"(d[11]), "=f"(d[12]), "=f"(d[13]), "=f"(d[14]), "=f"(d[15])
      : "r"(a[0]), "r"(a[1]), "r"(a[2]), "r"(a[3]), "r"(db), "n"(HB), "n"(0));
  }
};
template <> struct WgRS<64> {
  template <uint32_t HB>
  static __device__ __forceinline__ void mma(float* d, const uint32_t* a, uint32_t db) {
    asm volatile("{\n.reg .pred p;\n.reg .b64 db;\nsetp.ne.b32 p, %38, 0;\n"
      "mov.b64 db, {%36, %37};\n"
      "wgmma.mma_async.sync.aligned.m64n64k16.f32.bf16.bf16 {"
      "%0, %1, %2, %3, %4, %5, %6, %7, %8, %9, %10, %11, %12, %13, %14, %15, "
      "%16, %17, %18, %19, %20, %21, %22, %23, %24, %25, %26, %27, %28, %29, %30, %31"
      "}, {%32, %33, %34, %35}, db, p, 1, 1, 1;\n}\n"
      : "+f"(d[0]), "+f"(d[1]), "+f"(d[2]), "+f"(d[3]), "+f"(d[4]), "+f"(d[5]), "+f"(d[6]), "+f"(d[7]),
        "+f"(d[8]), "+f"(d[9]), "+f"(d[10]), "+f"(d[11]), "+f"(d[12]), "+f"(d[13]), "+f"(d[14]), "+f"(d[15]),
        "+f"(d[16]), "+f"(d[17]), "+f"(d[18]), "+f"(d[19]), "+f"(d[20]), "+f"(d[21]), "+f"(d[22]), "+f"(d[23]),
        "+f"(d[24]), "+f"(d[25]), "+f"(d[26]), "+f"(d[27]), "+f"(d[28]), "+f"(d[29]), "+f"(d[30]), "+f"(d[31])
      : "r"(a[0]), "r"(a[1]), "r"(a[2]), "r"(a[3]), "r"(db), "n"(HB), "n"(1));
  }
  template <uint32_t HB>
  static __device__ __forceinline__ void set(float* d, const uint32_t* a, uint32_t db) {
    asm volatile("{\n.reg .pred p;\n.reg .b64 db;\nsetp.ne.b32 p, %38, 0;\n"
      "mov.b64 db, {%36, %37};\n"
      "wgmma.mma_async.sync.aligned.m64n64k16.f32.bf16.bf16 {"
      "%0, %1, %2, %3, %4, %5, %6, %7, %8, %9, %10, %11, %12, %13, %14, %15, "
      "%16, %17, %18, %19, %20, %21, %22, %23, %24, %25, %26, %27, %28, %29, %30, %31"
      "}, {%32, %33, %34, %35}, db, p, 1, 1, 1;\n}\n"
      : "=f"(d[0]), "=f"(d[1]), "=f"(d[2]), "=f"(d[3]), "=f"(d[4]), "=f"(d[5]), "=f"(d[6]), "=f"(d[7]),
        "=f"(d[8]), "=f"(d[9]), "=f"(d[10]), "=f"(d[11]), "=f"(d[12]), "=f"(d[13]), "=f"(d[14]), "=f"(d[15]),
        "=f"(d[16]), "=f"(d[17]), "=f"(d[18]), "=f"(d[19]), "=f"(d[20]), "=f"(d[21]), "=f"(d[22]), "=f"(d[23]),
        "=f"(d[24]), "=f"(d[25]), "=f"(d[26]), "=f"(d[27]), "=f"(d[28]), "=f"(d[29]), "=f"(d[30]), "=f"(d[31])
      : "r"(a[0]), "r"(a[1]), "r"(a[2]), "r"(a[3]), "r"(db), "n"(HB), "n"(0));
  }
};
template <> struct WgSST<48> {
  template <uint32_t HA, uint32_t HB>
  static __device__ __forceinline__ void mma(float* d, uint32_t da, uint32_t db, int sc) {
    asm volatile("{\n.reg .pred p;\n.reg .b64 da, db;\nsetp.ne.b32 p, %28, 0;\n"
      "mov.b64 da, {%24, %25};\nmov.b64 db, {%26, %27};\n"
      "wgmma.mma_async.sync.aligned.m64n48k16.f32.bf16.bf16 {"
      "%0, %1, %2, %3, %4, %5, %6, %7, %8, %9, %10, %11, %12, %13, %14, %15, "
      "%16, %17, %18, %19, %20, %21, %22, %23"
      "}, da, db, p, 1, 1, 0, 1;\n}\n"
      : "+f"(d[0]), "+f"(d[1]), "+f"(d[2]), "+f"(d[3]), "+f"(d[4]), "+f"(d[5]), "+f"(d[6]), "+f"(d[7]),
        "+f"(d[8]), "+f"(d[9]), "+f"(d[10]), "+f"(d[11]), "+f"(d[12]), "+f"(d[13]), "+f"(d[14]), "+f"(d[15]),
        "+f"(d[16]), "+f"(d[17]), "+f"(d[18]), "+f"(d[19]), "+f"(d[20]), "+f"(d[21]), "+f"(d[22]), "+f"(d[23])
      : "r"(da), "n"(HA), "r"(db), "n"(HB), "r"(sc));
  }
};
template <> struct WgSST<80> {
  template <uint32_t HA, uint32_t HB>
  static __device__ __forceinline__ void mma(float* d, uint32_t da, uint32_t db, int sc) {
    asm volatile("{\n.reg .pred p;\n.reg .b64 da, db;\nsetp.ne.b32 p, %44, 0;\n"
      "mov.b64 da, {%40, %41};\nmov.b64 db, {%42, %43};\n"
      "wgmma.mma_async.sync.aligned.m64n80k16.f32.bf16.bf16 {"
      "%0, %1, %2, %3, %4, %5, %6, %7, %8, %9, %10, %11, %12, %13, %14, %15, "
      "%16, %17, %18, %19, %20, %21, %22, %23, %24, %25, %26, %27, %28, %29, %30, %31, "
      "%32, %33, %34, %35, %36, %37, %38, %39"
      "}, da, db, p, 1, 1, 0, 1;\n}\n"
      : "+f"(d[0]), "+f"(d[1]), "+f"(d[2]), "+f"(d[3]), "+f"(d[4]), "+f"(d[5]), "+f"(d[6]), "+f"(d[7]),
        "+f"(d[8]), "+f"(d[9]), "+f"(d[10]), "+f"(d[11]), "+f"(d[12]), "+f"(d[13]), "+f"(d[14]), "+f"(d[15]),
        "+f"(d[16]), "+f"(d[17]), "+f"(d[18]), "+f"(d[19]), "+f"(d[20]), "+f"(d[21]), "+f"(d[22]), "+f"(d[23]),
        "+f"(d[24]), "+f"(d[25]), "+f"(d[26]), "+f"(d[27]), "+f"(d[28]), "+f"(d[29]), "+f"(d[30]), "+f"(d[31]),
        "+f"(d[32]), "+f"(d[33]), "+f"(d[34]), "+f"(d[35]), "+f"(d[36]), "+f"(d[37]), "+f"(d[38]), "+f"(d[39])
      : "r"(da), "n"(HA), "r"(db), "n"(HB), "r"(sc));
  }
};
template <> struct WgSST<192> {
  template <uint32_t HA, uint32_t HB>
  static __device__ __forceinline__ void mma(float* d, uint32_t da, uint32_t db, int sc) {
    asm volatile("{\n.reg .pred p;\n.reg .b64 da, db;\nsetp.ne.b32 p, %100, 0;\n"
      "mov.b64 da, {%96, %97};\nmov.b64 db, {%98, %99};\n"
      "wgmma.mma_async.sync.aligned.m64n192k16.f32.bf16.bf16 {"
      "%0, %1, %2, %3, %4, %5, %6, %7, %8, %9, %10, %11, %12, %13, %14, %15, "
      "%16, %17, %18, %19, %20, %21, %22, %23, %24, %25, %26, %27, %28, %29, %30, %31, "
      "%32, %33, %34, %35, %36, %37, %38, %39, %40, %41, %42, %43, %44, %45, %46, %47, "
      "%48, %49, %50, %51, %52, %53, %54, %55, %56, %57, %58, %59, %60, %61, %62, %63, "
      "%64, %65, %66, %67, %68, %69, %70, %71, %72, %73, %74, %75, %76, %77, %78, %79, "
      "%80, %81, %82, %83, %84, %85, %86, %87, %88, %89, %90, %91, %92, %93, %94, %95"
      "}, da, db, p, 1, 1, 0, 1;\n}\n"
      : "+f"(d[0]), "+f"(d[1]), "+f"(d[2]), "+f"(d[3]), "+f"(d[4]), "+f"(d[5]), "+f"(d[6]), "+f"(d[7]),
        "+f"(d[8]), "+f"(d[9]), "+f"(d[10]), "+f"(d[11]), "+f"(d[12]), "+f"(d[13]), "+f"(d[14]), "+f"(d[15]),
        "+f"(d[16]), "+f"(d[17]), "+f"(d[18]), "+f"(d[19]), "+f"(d[20]), "+f"(d[21]), "+f"(d[22]), "+f"(d[23]),
        "+f"(d[24]), "+f"(d[25]), "+f"(d[26]), "+f"(d[27]), "+f"(d[28]), "+f"(d[29]), "+f"(d[30]), "+f"(d[31]),
        "+f"(d[32]), "+f"(d[33]), "+f"(d[34]), "+f"(d[35]), "+f"(d[36]), "+f"(d[37]), "+f"(d[38]), "+f"(d[39]),
        "+f"(d[40]), "+f"(d[41]), "+f"(d[42]), "+f"(d[43]), "+f"(d[44]), "+f"(d[45]), "+f"(d[46]), "+f"(d[47]),
        "+f"(d[48]), "+f"(d[49]), "+f"(d[50]), "+f"(d[51]), "+f"(d[52]), "+f"(d[53]), "+f"(d[54]), "+f"(d[55]),
        "+f"(d[56]), "+f"(d[57]), "+f"(d[58]), "+f"(d[59]), "+f"(d[60]), "+f"(d[61]), "+f"(d[62]), "+f"(d[63]),
        "+f"(d[64]), "+f"(d[65]), "+f"(d[66]), "+f"(d[67]), "+f"(d[68]), "+f"(d[69]), "+f"(d[70]), "+f"(d[71]),
        "+f"(d[72]), "+f"(d[73]), "+f"(d[74]), "+f"(d[75]), "+f"(d[76]), "+f"(d[77]), "+f"(d[78]), "+f"(d[79]),
        "+f"(d[80]), "+f"(d[81]), "+f"(d[82]), "+f"(d[83]), "+f"(d[84]), "+f"(d[85]), "+f"(d[86]), "+f"(d[87]),
        "+f"(d[88]), "+f"(d[89]), "+f"(d[90]), "+f"(d[91]), "+f"(d[92]), "+f"(d[93]), "+f"(d[94]), "+f"(d[95])
      : "r"(da), "n"(HA), "r"(db), "n"(HB), "r"(sc));
  }
};

struct FftConst {
  uint32_t f[2][4], fi[4][4];
  uint32_t ta[2][2], tb[2][2];
};
__device__ __forceinline__ void cis(int m, float scale, float& c, float& s) {
  const float a = (float)m * (-6.283185307179586f * scale);
  c = __cosf(a);
  s = __sinf(a);
}
__device__ __forceinline__ void fft_tables(uint32_t (&v)[12], int tw) {
  const int row = tw >> 2, ch = tw & 3;
#pragma unroll
  for (int i = 0; i < 4; i++) {
    float c[2], s[2], x[2];
#pragma unroll
    for (int e = 0; e < 2; e++) {
      cis((((32 * (8 * ch + 2 * i + e) + 15) * (4 * row - 63) + 2048) & 4095) - 2048, 1.f / 4096, c[e], s[e]);
      float gc, gs;
      cis((((row & 15) * (8 * (ch & 1) + 2 * i + e) + 8) & 15) - 8, 1.f / 16, gc, gs);
      x[e] = (row >> 4) == (ch >> 1) ? gc : (ch >> 1) ? gs : -gs;
    }
    v[i] = pack2(c[0] * 0.125f, c[1] * 0.125f);
    v[4 + i] = pack2(s[0] * 0.125f, s[1] * 0.125f);
    v[8 + i] = pack2(x[0], x[1]);
  }
#pragma unroll
  for (int i = 0; i < 12; i++) asm volatile("" : "+r"(v[i]));
}
__device__ __forceinline__ void fft_tables_store(const uint32_t (&v)[12], uint32_t sb, int tw) {
  const int row = tw >> 2;
  const uint32_t x = ((tw ^ (row >> 1)) & 3) << 4, a = sb + OFF_FT + (16 * (row >> 3) + (row & 7)) * 64 + x;
  sts128(a, v[0], v[1], v[2], v[3]);
  sts128(a + 512, v[4], v[5], v[6], v[7]);
  sts128(sb + OFF_GT + row * 64 + x, v[8], v[9], v[10], v[11]);
}
__device__ __forceinline__ void fft_twiddles(uint32_t (&v)[2], int tw) {
  float a[2], s[2];
#pragma unroll
  for (int i = 0; i < 2; i++) {
    float c;
    cis((2 * (2 * (tw & 3) + i) - 15) * (4 * (tw >> 2) - 63), 1.f / 4096, c, s[i]);
    a[i] = __fdividef(-s[i], 1.f + c);
  }
  v[0] = pack2(a[0], a[1]);
  v[1] = pack2(s[0], s[1]);
  asm volatile("" : "+r"(v[0]), "+r"(v[1]));
}
__device__ __forceinline__ void fft_matrices(FftConst& k, uint32_t sb, int w, int lane) {
  const uint32_t x = (lane >> 1) & 3;
  const uint2 t0 = lds64(sb + OFF_TT + 256 * w + 8 * lane), t1 = lds64(sb + OFF_TT + 256 * w + 8 * (lane ^ 3));
  k.ta[0][0] = t0.x;
  k.tb[0][0] = t0.y;
  k.ta[1][1] = __byte_perm(t1.x, 0, 0x1032);
  k.tb[1][1] = __byte_perm(t1.y, 0, 0x1032);
#pragma unroll
  for (int j = 0; j < 2; j++) {
    k.ta[1 - j][j] = k.ta[j][j] ^ 0x80008000u;
    k.tb[1 - j][j] = k.tb[j][j] ^ 0x80008000u;
    asm volatile("" : "+r"(k.ta[0][j]), "+r"(k.tb[0][j]), "+r"(k.ta[1][j]), "+r"(k.tb[1][j]));
  }
#pragma unroll
  for (int i = 0; i < 2; i++) {
    ldsm4(k.f[i], sb + OFF_FT + (16 * w + (lane & 15)) * 64 + (((2 * i + (lane >> 4)) ^ x) << 4));
    ldsm4t(k.fi[i], sb + OFF_FT + (32 * i + lane) * 64 + ((w ^ x) << 4));
#pragma unroll
    for (int j = 0; j < 4; j++) {
      k.fi[2 + i][j] = (j & 1) ? k.fi[i][j - 1] ^ 0x80008000u : k.fi[i][j + 1];
      asm volatile("" : "+r"(k.fi[2 + i][j]));
    }
  }
}
__device__ __forceinline__ void rot(uint32_t& x, uint32_t& y, uint32_t a, uint32_t b) {
  x = bfma(a, y, x);
  y = bfma(b, x, y);
  x = bfma(a, y, x);
}
__device__ __forceinline__ void twiddle_fwd(uint32_t (&a)[4][4], float* d, const FftConst& k) {
#pragma unroll
  for (int q = 0; q < 4; q++)
#pragma unroll
    for (int j = 0; j < 2; j++) {
      const float* x = d + 8 * q + 4 * j;
      uint32_t re = pack2(x[0], x[1]), im = pack2(x[2], x[3]);
      rot(re, im, k.ta[0][j], k.tb[0][j]);
      a[q & 2][2 * j + (q & 1)] = re;
      a[(q & 2) + 1][2 * j + (q & 1)] = im;
    }
}
__device__ __forceinline__ void g_step(float* d, const uint32_t (&a)[4][4], uint32_t dre, uint32_t dim) {
  WgRS<32>::set<HI_SW64>(d, a[0], dre);
  WgRS<32>::set<HI_SW64>(d + 16, a[2], dre);
  WgRS<32>::mma<HI_SW64>(d, a[1], dim);
  WgRS<32>::mma<HI_SW64>(d + 16, a[3], dim);
  wg_commit();
}

__device__ __forceinline__ void conv_channel(const FftConst& k, uint32_t sb, int c, int wg, int w, int lane) {
  const uint32_t cb = sb + off_ch(c), bars = sb + OFF_BAR;
  const uint32_t du = desc_lo(cb, 1024), dg = desc_lo(sb + OFF_GT, 16), dz = desc_lo(cb + U_BYTES, 16);
  float U[32], H[32];
  uint32_t a[4][4], e[4][4];
  const float dv = __uint_as_float(lds32(sb + OFF_D + 4 * c));
  wg_fence();
  WgRS<64>::set<HI_SW32>(H, k.f[0], du + 256);
  WgRS<64>::mma<HI_SW32>(H, k.f[1], du + 256 + 32);
  wg_commit();
  wg_wait<0>();
  pin<32>(H);
  twiddle_fwd(a, H, k);
  if (ATT_GATE && H_EARLY) mbar_wait(bars + 8 * B_ATTN, 0);
  mbar_wait(bars + 8 * (B_U + (c < 3 ? c : 3)), 0);
  TSM(w == 0 && c < 3, 7 + wg);
  wg_fence();
  WgRS<64>::set<HI_SW32>(U, k.f[0], du);
  WgRS<64>::mma<HI_SW32>(U, k.f[1], du + 32);
  wg_commit();
  g_step(H, a, dg, dg + 64);
  wg_wait<1>();
  pin<32>(U);
  twiddle_fwd(e, U, k);
  wg_fence();
  g_step(U, e, dg, dg + 64);
  wg_wait<0>();
  pin<32>(U);
  pin<32>(H);
#pragma unroll
  for (int j = 0; j < 2; j++) {
    float pr[4][2], pi[4][2];
#pragma unroll
    for (int x = 0; x < 2; x++) {
      H[4 * j + x] += dv;
#pragma unroll
      for (int m = 0; m < 4; m++) {
#pragma unroll
        for (int q = 0; q <= m; q++) {
          const int ih = 16 * (q >> 1) + 2 * (q & 1) + 4 * j + x, iu = 16 * ((m - q) >> 1) + 2 * ((m - q) & 1) + 4 * j + x;
          pr[m][x] = q ? fmaf(H[ih], U[iu], pr[m][x]) : H[ih] * U[iu];
          pi[m][x] = q ? fmaf(H[ih], U[iu + 8], pi[m][x]) : H[ih] * U[iu + 8];
          pr[m][x] = fmaf(-H[ih + 8], U[iu + 8], pr[m][x]);
          pi[m][x] = fmaf(H[ih + 8], U[iu], pi[m][x]);
        }
      }
    }
#pragma unroll
    for (int m = 0; m < 4; m++) {
      a[m & 2][2 * j + (m & 1)] = pack2(pr[m][0], pr[m][1]);
      a[(m & 2) + 1][2 * j + (m & 1)] = pack2(pi[m][0], pi[m][1]);
    }
  }
  wg_fence();
  g_step(U, a, dg + 64, dg);
  const uint32_t za = cb + U_BYTES + (8 * w + (lane & 7)) * 128 + (((lane >> 3) ^ (lane & 7)) << 4);
  const uint32_t ya = cb + (lane >> 4) * 1024 + (8 * w + (lane & 7)) * 32 + ((((lane >> 3) ^ (lane >> 2)) & 1) << 4);
  wg_sync(1 + wg);
  wg_wait<0>();
  pin<32>(U);
  TSIF(w == 0, 80 + c);
#pragma unroll
  for (int p = 0; p < 2; p++) {
#pragma unroll
    for (int i = 0; i < 4; i++) {
      const int j = i & 1;
      const float* x = U + 16 * p + 4 * j + (i & 2);
      e[p][i] = pack2(x[8], x[9]);
      e[2 + p][i] = pack2(x[0], x[1]);
      rot(e[p][i], e[2 + p][i], k.ta[1][j], k.tb[1][j]);
    }
    stsm4(za ^ (64 * p), e[p]);
    stsm4((za ^ (64 * p)) + 4096, e[2 + p]);
  }
  fence_async_smem();
  wg_sync(1 + wg);
  wg_fence();
  WgRS<64>::set<HI_SW128>(H, k.fi[0], dz);
#pragma unroll
  for (int ks = 1; ks < 4; ks++) WgRS<64>::mma<HI_SW128>(H, k.fi[ks], dz + 128 * ks);
  wg_commit();
  wg_wait<0>();
  pin<32>(H);
  TSIF(w == 0, 88 + c);
#pragma unroll
  for (int j = 0; j < 8; j++)
    a[j >> 2][j & 3] = j < 2 ? pack2(H[4 * j], H[4 * j + 1]) : pack2(H[4 * j] + H[4 * j - 6], H[4 * j + 1] + H[4 * j - 5]);
  stsm4(ya, a[0]);
  stsm4(ya + 2048, a[1]);
  fence_async_smem();
  __syncwarp();
}

__device__ __forceinline__ void prep_slab(uint4* res, const uint2* sw, uint32_t sb, int slab, int w, int lane) {
  const int t = lane & 3, tp = (lane & 7) >> 1, pos = 8 * tp + 2 * (((lane >> 3) + tp) & 3) + (lane & 1);
  const uint32_t base = sb + OFF_KVS + slab * KVS_BYTES + pos * 128;
  uint32_t kk[2][4][4], vv[2][4];
  mbar_wait(sb + OFF_BAR + 8 * (B_KV + slab), 0);
#pragma unroll
  for (int h = 0; h < 2; h++) {
#pragma unroll
    for (int j = 0; j < 4; j++) {
      const uint32_t a = base + 128 * j;
      ldsm4t(kk[h][j], a + (((w + 4 * h) ^ ((a >> 7) & 7)) << 4));
    }
    const uint32_t a = base + KVS_V;
    ldsm4t(vv[h], a + (((w + 4 * h) ^ ((a >> 7) & 7)) << 4));
  }
#pragma unroll
  for (int h = 0; h < 2; h++) {
    uint32_t (&k)[4][4] = kk[h];
    uint32_t (&v)[4] = vv[h];
    const uint32_t w0 = __byte_perm(sw[h].x, 0, 0x1010), w1 = __byte_perm(sw[h].x, 0, 0x3232);
    const uint32_t w2 = __byte_perm(sw[h].y, 0, 0x1010), w3 = __byte_perm(sw[h].y, 0, 0x3232);
#pragma unroll
    for (int m = 0; m < 4; m++)
      v[m] = bmul(badd(badd(badd(bmul(k[0][m], w3), bmul(k[1][m], w2)), bmul(k[2][m], w1)), bmul(k[3][m], w0)), v[m]);
    uint32_t a[4];
#pragma unroll
    for (int m = 0; m < 4; m++) a[m] = (t & 1) ? v[(m + 3) & 3] : v[m];
    res[h] = (t & 2) ? make_uint4(a[2], a[3], a[0], a[1]) : make_uint4(a[0], a[1], a[2], a[3]);
  }
}

__device__ __forceinline__ void prep_gate(const Params& p, int b, int w, int lane) {
  uint2 gw[5], x[4][5];
#pragma unroll
  for (int j = 0; j < 5; j++) gw[j] = ldg64(reinterpret_cast<const uint2*>(p.gate_w) + lane + 32 * j);
#pragma unroll
  for (int i = 0; i < 4; i++)
#pragma unroll
    for (int j = 0; j < 5; j++)
      x[i][j] = ldg64(reinterpret_cast<const uint2*>(p.q) + (16 * b + 4 * w + i) * (DIM / 4) + lane + 32 * j);
  float s[4];
#pragma unroll
  for (int i = 0; i < 4; i++) {
    s[i] = 0.f;
#pragma unroll
    for (int j = 0; j < 5; j++) {
      const uint32_t m0 = bmul(x[i][j].x, gw[j].x), m1 = bmul(x[i][j].y, gw[j].y);
      s[i] += (bf_lo(m0) + bf_hi(m0)) + (bf_lo(m1) + bf_hi(m1));
    }
  }
  const bool h = lane & 16, q = lane & 8;
  const float a = (h ? s[2] : s[0]) + __shfl_xor_sync(0xffffffffu, h ? s[0] : s[2], 16);
  const float c = (h ? s[3] : s[1]) + __shfl_xor_sync(0xffffffffu, h ? s[1] : s[3], 16);
  float z = (q ? c : a) + __shfl_xor_sync(0xffffffffu, q ? a : c, 8);
#pragma unroll
  for (int o = 4; o > 0; o >>= 1) z += __shfl_xor_sync(0xffffffffu, z, o);
  z = bf_lo(pack2(z, 0.f));
  if ((lane & 7) == 0) g_gate[16 * b + 4 * w + (lane >> 3)] = bf_lo(pack2(__fdividef(1.f, 1.f + __expf(-z)), 0.f));
}

__device__ __forceinline__ uint32_t bmax(uint32_t a, uint32_t b) {
  uint32_t d;
  asm("max.bf16x2 %0, %1, %2;" : "=r"(d) : "r"(a), "r"(b));
  return d;
}
__device__ __forceinline__ void softmax_two(const float (&l)[2][2], uint32_t& p0, uint32_t& p1) {
  constexpr float kScale = 0.22360679774997896f, kLog2e = 1.4426950408889634f;
  const uint32_t r0 = pack2(l[0][0], l[1][0]), r1 = pack2(l[0][1], l[1][1]);
  const uint32_t x0 = pack2(bf_lo(r0) * kScale, bf_hi(r0) * kScale), x1 = pack2(bf_lo(r1) * kScale, bf_hi(r1) * kScale);
  uint32_t m = bmax(x0, x1);
  m = bmax(m, __shfl_xor_sync(0xffffffffu, m, 1));
  m = bmax(m, __shfl_xor_sync(0xffffffffu, m, 2));
  const float m0 = bf_lo(m) * kLog2e, m1 = bf_hi(m) * kLog2e;
  p0 = pack2(ex2(bf_lo(x0) * kLog2e - m0), ex2(bf_lo(x1) * kLog2e - m0));
  p1 = pack2(ex2(bf_hi(x0) * kLog2e - m1), ex2(bf_hi(x1) * kLog2e - m1));
}

__device__ __forceinline__ void halo_read(uint32_t (&kpv)[10], uint32_t (&vpv)[10], uint32_t (&tg)[7], const uint4* hp) {
#pragma unroll
  for (int j = 0; j < 7; j++) {
    uint32_t x0, x1, x2;
    asm volatile("ld.relaxed.gpu.global.v4.u32 {%0, %1, %2, %3}, [%4];"
                 : "=r"(x0), "=r"(x1), "=r"(x2), "=r"(tg[j]) : "l"(hp + 32 * j) : "memory");
    if (j < 4) kpv[3 * j] = x0; else vpv[3 * j - 10] = x0;
    if (j < 3) kpv[3 * j + 1] = x1; else vpv[3 * j - 9] = x1;
    if (j < 3) kpv[3 * j + 2] = x2; else if (j < 6) vpv[3 * j - 8] = x2;
  }
}

template <int ROT>
__device__ __forceinline__ void pack_qkv(const float* acc, uint32_t (&qlo)[10], uint32_t (&qhi)[10], uint32_t (&klo)[10],
                                         uint32_t (&khi)[10], uint32_t (&vlo)[10], uint32_t (&vhi)[10]) {
#pragma unroll
  for (int j = 0; j < 10; j++) {
    const int x = (j + ROT) % 10, tq = x < 8 ? x : 16 + x, tk = x < 8 ? 8 + x : 18 + x, tv = x < 8 ? 16 + x : 20 + x;
    khi[j] = pack2(acc[4 * tk + 2], acc[4 * tk + 3]);
    vhi[j] = movm(pack2(acc[4 * tv + 2], acc[4 * tv + 3]));
    qlo[j] = pack2(acc[4 * tq], acc[4 * tq + 1]);
    qhi[j] = pack2(acc[4 * tq + 2], acc[4 * tq + 3]);
    klo[j] = pack2(acc[4 * tk], acc[4 * tk + 1]);
    vlo[j] = pack2(acc[4 * tv], acc[4 * tv + 1]);
    asm volatile("" : "+r"(khi[j]), "+r"(qlo[j]), "+r"(qhi[j]), "+r"(klo[j]), "+r"(vlo[j]));
  }
}

template <int ROT> __device__ __forceinline__ void halo_send(const float* acc, uint4* ho, uint32_t tag) {
#pragma unroll
  for (int j = 0; j < 7; j++) {
    uint32_t x[3];
#pragma unroll
    for (int e = 0; e < 3; e++) {
      const int i = 3 * j + e, y = (i % 10 + ROT) % 10, tk = y < 8 ? 8 + y : 18 + y, tv = y < 8 ? 16 + y : 20 + y;
      x[e] = i < 10 ? pack2(acc[4 * tk + 2], acc[4 * tk + 3]) : i < 20 ? movm(pack2(acc[4 * tv + 2], acc[4 * tv + 3])) : 0u;
    }
    asm volatile("st.relaxed.gpu.global.v4.u32 [%0], {%1, %2, %3, %4};" ::"l"(ho + 32 * j), "r"(x[0]), "r"(x[1]), "r"(x[2]), "r"(tag) : "memory");
  }
}

__device__ __forceinline__ void attention(float* acc, uint32_t sb, int b, int par, int w, int lane, uint32_t tag) {
  const int g = lane >> 2, t = lane & 3;
  uint32_t klo[10], khi[10], vlo[10], vhi[10], qlo[10], qhi[10], kpv[10], vpv[10];
  if (HALO_FIRST && w == 3 && b < NCTA - 8) {
    uint4* ho = g_halo + (b * 2 + par) * 224 + lane;
    if (tail_first(b & 7)) halo_send<8>(acc, ho, tag);
    else halo_send<0>(acc, ho, tag);
    TSIF(par == 0, 76);
    pin<120>(acc);
  }
  if (tail_first(b & 7)) pack_qkv<8>(acc, qlo, qhi, klo, khi, vlo, vhi);
  else pack_qkv<0>(acc, qlo, qhi, klo, khi, vlo, vhi);
  const uint32_t xa = sb + OFF_KVX + (par * 3) * 2560 + lane * 16;
  if (w < 3) {
    sts128(xa + w * 2560, khi[0], khi[1], khi[2], khi[3]);
    sts128(xa + w * 2560 + 512, khi[4], khi[5], khi[6], khi[7]);
    sts128(xa + w * 2560 + 1024, khi[8], khi[9], vhi[0], vhi[1]);
    sts128(xa + w * 2560 + 1536, vhi[2], vhi[3], vhi[4], vhi[5]);
    sts128(xa + w * 2560 + 2048, vhi[6], vhi[7], vhi[8], vhi[9]);
  } else if (!HALO_FIRST && b < NCTA - 8) {
    uint4* ho = g_halo + (b * 2 + par) * 224 + lane;
#pragma unroll
    for (int j = 0; j < 7; j++) {
      const uint32_t x0 = j < 4 ? khi[3 * j] : vhi[3 * j - 10], x1 = j < 3 ? khi[3 * j + 1] : vhi[3 * j - 9];
      const uint32_t x2 = j < 3 ? khi[3 * j + 2] : j < 6 ? vhi[3 * j - 8] : 0u;
      asm volatile("st.relaxed.gpu.global.v4.u32 [%0], {%1, %2, %3, %4};" ::"l"(ho + 32 * j), "r"(x0), "r"(x1), "r"(x2), "r"(tag) : "memory");
    }
  }
  TSIF(par == 0 && w == 1, 64);
  TSIF(par == 0 && w == 3 && !HALO_FIRST, 76);
#pragma unroll
  for (int j = 0; j < 10; j++) vlo[j] = movm(vlo[j]);
  const bool far0 = 2 * t > g, far1 = 2 * t + 1 > g;
  const uint32_t mfar = (far0 ? 0x0000FFFFu : 0u) | (far1 ? 0xFFFF0000u : 0u);
  float slo[4][2], shi[4][2], lg[2][2];
  uint32_t phi[4], plo[4], qml[4], qmh[4];
#pragma unroll
  for (int h = 0; h < 4; h++) {
    const int f = h == 0 ? 0 : h == 1 ? 3 : h == 2 ? 5 : 8, hf = h < 2 ? 2 : 7;
    const bool mine = (h & 1) ? t >= 2 : t < 2;
    qml[h] = mine ? qlo[hf] : 0u;
    qmh[h] = mine ? qhi[hf] : 0u;
    float a[4] = {0.f, 0.f, 0.f, 0.f}, c[4] = {0.f, 0.f, 0.f, 0.f};
    mma16816(a, qlo[f], qhi[f], qlo[f + 1], qhi[f + 1], klo[f], klo[f + 1]);
    mma16816(c, qlo[f], qhi[f], qlo[f + 1], qhi[f + 1], khi[f], khi[f + 1]);
    mma1688(a, qml[h], qmh[h], klo[hf]);
    mma1688(c, qml[h], qmh[h], khi[hf]);
    slo[h][0] = a[0];
    slo[h][1] = a[1];
    shi[h][0] = lg[h & 1][0] = far0 ? a[2] : c[2];
    shi[h][1] = lg[h & 1][1] = far1 ? a[3] : c[3];
    if (!ATT_MERGE && (h & 1)) softmax_two(lg, phi[h - 1], phi[h]);
  }
  TSIF(par == 0 && w == 1, 65);
  wg_sync(1 + par);
  TSIF(par == 0 && w == 1, 66);
  const bool nohist = (w == 0) && (b < 8);
  const uint4* hp = g_halo + ((b - 8) * 2 + par) * 224 + lane;
  uint32_t tg[7];
  if (w > 0) {
    const uint4 v0 = lds128(xa + (w - 1) * 2560), v1 = lds128(xa + (w - 1) * 2560 + 512), v2 = lds128(xa + (w - 1) * 2560 + 1024);
    const uint4 v3 = lds128(xa + (w - 1) * 2560 + 1536), v4 = lds128(xa + (w - 1) * 2560 + 2048);
    kpv[0] = v0.x; kpv[1] = v0.y; kpv[2] = v0.z; kpv[3] = v0.w; kpv[4] = v1.x; kpv[5] = v1.y; kpv[6] = v1.z; kpv[7] = v1.w;
    kpv[8] = v2.x; kpv[9] = v2.y; vpv[0] = v2.z; vpv[1] = v2.w; vpv[2] = v3.x; vpv[3] = v3.y; vpv[4] = v3.z; vpv[5] = v3.w;
    vpv[6] = v4.x; vpv[7] = v4.y; vpv[8] = v4.z; vpv[9] = v4.w;
  } else if (nohist) {
#pragma unroll
    for (int j = 0; j < 10; j++) kpv[j] = vpv[j] = 0u;
  } else {
    TSIF(par == 0, 77);
    halo_read(kpv, vpv, tg, hp);
  }
  if (w == 0 && !nohist) {
    int spins = 0;
    while (true) {
      bool ok = true;
#pragma unroll
      for (int j = 0; j < 7; j++) ok = ok && tg[j] == tag;
      if (__all_sync(0xffffffffu, ok) || ++spins > SPIN_LIMIT) break;
      halo_read(kpv, vpv, tg, hp);
    }
    TSIF(par == 0, 79);
  }
#pragma unroll
  for (int h = 0; h < 4; h++) {
    const int f = h == 0 ? 0 : h == 1 ? 3 : h == 2 ? 5 : 8, hf = h < 2 ? 2 : 7;
    float a[4] = {0.f, 0.f, 0.f, 0.f};
    mma16816(a, qlo[f], qhi[f], qlo[f + 1], qhi[f + 1], kpv[f], kpv[f + 1]);
    mma1688(a, qml[h], qmh[h], kpv[hf]);
    const float ninf = __int_as_float(0xff800000);
    lg[h & 1][0] = far0 ? (nohist ? ninf : a[0]) : slo[h][0];
    lg[h & 1][1] = far1 ? (nohist ? ninf : a[1]) : slo[h][1];
    if (h & 1) {
      softmax_two(lg, plo[h - 1], plo[h]);
      if (ATT_MERGE) {
        const float lh[2][2] = {{shi[h - 1][0], shi[h - 1][1]}, {shi[h][0], shi[h][1]}};
        softmax_two(lh, phi[h - 1], phi[h]);
      }
    }
  }
  TSIF(par == 0 && w <= 1, 67 + w);
  uint32_t ov[20];
#pragma unroll
  for (int hp = 0; hp < 2; hp++) {
    const int hf = hp ? 7 : 2;
    float sh[4] = {0.f, 0.f, 0.f, 0.f}, i0 = 0.f, i1 = 0.f;
#pragma unroll
    for (int e = 0; e < 2; e++) {
      const int h = 2 * hp + e, f = h == 0 ? 0 : h == 1 ? 3 : h == 2 ? 5 : 8;
      const uint32_t a0 = plo[h] & mfar, a2 = plo[h] & ~mfar, a3 = phi[h] & mfar, c1 = phi[h] & ~mfar;
      float sum[4] = {0.f, 0.f, 0.f, 0.f};
      mma1688(sum, plo[h], phi[h], 0x3F803F80u);
      const float r0 = rcp(sum[0]), r1 = rcp(sum[2]);
#pragma unroll
      for (int j = f; j < f + 2; j++) {
        float o[4] = {0.f, 0.f, 0.f, 0.f};
        mma16816(o, a0, 0u, a2, a3, vpv[j], vlo[j]);
        mma1688(o, 0u, c1, vhi[j]);
        ov[2 * j] = pack2(o[0] * r0, o[1] * r0);
        ov[2 * j + 1] = pack2(o[2] * r1, o[3] * r1);
      }
      const bool mine = e ? g >= 4 : g < 4;
      mma16816(sh, a0, 0u, a2, a3, mine ? vpv[hf] : 0u, mine ? vlo[hf] : 0u);
      mma1688(sh, 0u, c1, mine ? vhi[hf] : 0u);
      if (e == 0 || t >= 2) {
        i0 = r0;
        i1 = r1;
      }
    }
    ov[2 * hf] = pack2(sh[0] * i0, sh[1] * i0);
    ov[2 * hf + 1] = pack2(sh[2] * i1, sh[3] * i1);
  }
  TS(32 + 4 * par + w);
  mbar_wait(sb + OFF_BAR + 8 * B_P1, 0);
  const uint32_t oa = sb + OFF_OA + (lane >> 4) * 2048 + (32 * w + 2 * (lane & 15) + par) * 16;
#pragma unroll
  for (int j = 0; j < 5; j++) stsm4(oa + 4096 * j, ov + 4 * j);
  TSIF(par == 0 && w == 0, 120);
  fence_async_smem();
  TSIF(par == 0 && w == 0, 121);
  __syncwarp();
  if (lane == 0) mbar_arrive(sb + OFF_BAR + 8 * B_ATTN);
  TSM(w == 0 || w == 2, 122 + par + (w == 2 ? 3 : 0));
}

struct Maps {
  CUtensorMap x, wm, wt, k, v, y, wo, qm, qt, om, ot, u;
};

__device__ __forceinline__ void load_stage(uint32_t sb, int kb, int b, const Maps& m) {
  const uint32_t st = sb + (kb & 3) * STAGE_BYTES, bar = sb + OFF_BAR + 8 * (B_FULL1 + (kb & 3));
  const int r = b >> 3, hg = b & 7, slab = kb - KV_KB;
  const bool kv = slab >= 0 && slab < 5;
  const uint32_t kbar = sb + OFF_BAR + 8 * (B_KV + slab), dst = sb + OFF_KVS + slab * KVS_BYTES;
  mbar_expect_tx(bar, STAGE_BYTES);
  if (kv) mbar_expect_tx(kbar, KVS_BYTES);
  tma_3d(st, &m.x, 64 * kb, 64 * r, 0, bar);
  if (kv && KV_MIX) tma_3d(dst, &m.k, 0, 32 * (b >> 1) - 3, 2 * slab + (b & 1), kbar);
  tma_3d(st + ST_W, &m.wm, 80 * hg + (tail_first(hg) ? 16 : 0), 64 * kb, 0, bar);
  if (kv && KV_MIX) tma_3d(dst + KVS_V, &m.v, 0, 32 * (b >> 1), 2 * slab + (b & 1), kbar);
  tma_3d(st + ST_WT, &m.wt, 80 * hg + (tail_first(hg) ? 0 : 64), 64 * kb, 0, bar);
  if (kv && !KV_MIX) tma_3d(dst, &m.k, 0, 32 * (b >> 1) - 3, 2 * slab + (b & 1), kbar);
  if (kv && !KV_MIX) tma_3d(dst + KVS_V, &m.v, 0, 32 * (b >> 1), 2 * slab + (b & 1), kbar);
}

__global__ void __launch_bounds__(NTHR, 1) fused_kernel(const __grid_constant__ Maps m, const Params p) {
  extern __shared__ __align__(1024) uint8_t smem[];
  const uint32_t sb = (uint32_t)__cvta_generic_to_shared(smem);
  const uint32_t bars = sb + OFF_BAR;
  const int tid = threadIdx.x, lane = tid & 31;
  int b = blockIdx.x;
  if (BMAP == 1) b = (((b & 63) >> 3) * 2 + (b & 1)) * 8 + (((b < 64 ? 0x6521 : 0x7430) >> (4 * ((b >> 1) & 3))) & 7);
  if (BMAP == 2) b = ((b & 63) >> 2) * 8 + (((b < 64 ? 0x6521 : 0x7430) >> (4 * (b & 3))) & 7);
  if (BMAP == 3) b = (((b & 63) >> 3) * 2 + (b & 1)) * 8 + (((b < 64 ? 0x7430 : 0x6521) >> (4 * ((b >> 1) & 3))) & 7);
  if (BMAP == 4) b = (((b >> 4) * 2 + (b & 1)) * 8) + ((b >> 1) & 7);
  if (BMAP == 5) b = 127 - b;
  const int r = b >> 3, hg = b & 7;

  if (tid == T_ISSUE) {
    TSM(true, 0);
#pragma unroll
    for (int i = 0; i < 4; i++) mbar_init(bars + 8 * (B_FULL1 + i), 1);
#pragma unroll
    for (int i = 0; i < 3; i++) mbar_init(bars + 8 * (B_KV + i), 1);
    fence_async_smem();
#pragma unroll 1
    for (int kb = 0; kb <= PRE2; kb++) load_stage(sb, kb, b, m);
  } else if (tid >= T_PF && tid < T_PF + 12) {
    tm_prefetch(&m.x + (tid - T_PF));
  } else if (tid == T_INIT) {
#pragma unroll
    for (int i = 0; i < 4; i++) mbar_init(bars + 8 * (B_EMPTY1 + i), 8);
#pragma unroll
    for (int i = 0; i < 8; i++) mbar_init(bars + 8 * (B_FULL2 + i), 1);
#pragma unroll
    for (int i = 0; i < 4; i++) mbar_init(bars + 8 * (B_EMPTY2 + i), 8);
#pragma unroll
    for (int i = 0; i < 4; i++) mbar_init(bars + 8 * (B_U + i), 1);
    mbar_init(bars + 8 * B_HA, 4);
    mbar_init(bars + 8 * B_GATE, 4);
    mbar_init(bars + 8 * B_HB, 1);
    mbar_init(bars + 8 * B_KVD, 4);
    mbar_init(bars + 8 * B_QF, 1);
    mbar_init(bars + 8 * B_ATTN, 8);
    mbar_init(bars + 8 * B_P1, 8);
    mbar_init(bars + 8 * B_C34, 1);
#pragma unroll
    for (int i = 0; i < 5; i++) mbar_init(bars + 8 * (B_YST + i), 4);
#pragma unroll
    for (int i = 0; i < 5; i++) mbar_init(bars + 8 * (B_US + i), 4);
    mbar_init(bars + 8 * B_YSIG, 1);
    mbar_init(bars + 8 * B_YFULL, 1);
    mbar_init(bars + 8 * B_EPOCH, 1);
    mbar_init(bars + 8 * B_PREP, 4);
    mbar_init(bars + 8 * B_USIG, 1);
    mbar_init(bars + 8 * B_WST, 1);
#pragma unroll
    for (int i = 3; i < 5; i++) mbar_init(bars + 8 * (B_KV + i), 1);
    mbar_init(bars + 8 * B_E3, 8);
    mbar_init(bars + 8 * B_LAST, 1);
    mbar_init(bars + 8 * B_OSIG, 1);
    mbar_init(bars + 8 * B_WOP, 1);
    fence_async_smem();
  }
  const int warp = __shfl_sync(0xffffffffu, tid >> 5, 0), wg = warp >> 2, w = warp & 3;
  __syncthreads();

  if (wg == 3) {
    asm volatile("setmaxnreg.dec.sync.aligned.u32 56;");
    if (w == 0) {
      if (lane == 0) {
#pragma unroll 1
        for (int kb = 1 + PRE2; kb < 10; kb++) {
          if (kb >= 4) mbar_wait(bars + 8 * (kb == 7 ? B_E3 : B_EMPTY1 + (kb & 3)), (kb >> 3) & 1);
          TSIF(kb >= 4, 44 + kb);
          load_stage(sb, kb, b, m);
          TSIF(kb == 3, 60);
          if (kb == TRIG_KB) mbar_arrive(bars + 8 * B_LAST);
        }
        mbar_wait(bars + 8 * B_WOP, 0);
        mbar_wait(bars + 8 * WL_TRIG, 0);
        mbar_wait(bars + 8 * B_EPOCH, 0);
        flag_wait(g_cnt + C_W + 32 * hg, (lds32(sb + OFF_EPOCH) + 1) * 16);
        TS(30);
#pragma unroll 1
        for (int j = 0; j < 8; j++) {
          if (j >= 6) mbar_wait(bars + 8 * (B_EMPTY2 + j - 6), 0);
          if (j == 4) mbar_wait(bars + 8 * B_ATTN, 0);
          TSIF(j >= 6, 100 + j);
          if (RF_GATE && j == 6) mbar_wait(bars + 8 * B_YSIG, 0);
          mbar_expect_tx(bars + 8 * (B_FULL2 + j), j == 0 ? WO_BYTES : j == 5 ? O_BYTES + WO_BYTES + 512 : O_BYTES + WO_BYTES);
          bulk_load(sb + off_w(j), g_WO + (hg * 8 + step_src(hg, j)) * 800, WO_BYTES, bars + 8 * (B_FULL2 + j));
        }
        mbar_wait(bars + 8 * (B_EMPTY2 + 3), 0);
        mbar_expect_tx(bars + 8 * B_QF, O_BYTES);
        tma_2d(sb + OFF_QS, &m.qm, 80 * hg, 128 * r, bars + 8 * B_QF);
        tma_2d(sb + OFF_QT, &m.qt, 80 * hg + 64, 128 * r, bars + 8 * B_QF);
      }
    } else if (w == 1) {
      unsigned epoch = 0;
      if (lane == 0) {
        epoch = atomicAdd(g_cnt + C_LAUNCH, 1u) / NCTA;
        asm volatile("st.shared.u32 [%0], %1;" ::"r"(sb + OFF_EPOCH), "r"(epoch) : "memory");
        mbar_arrive(bars + 8 * B_EPOCH);
        mbar_wait(bars + 8 * B_KVD, 0);
        mbar_expect_tx(bars + 8 * B_HB, 5 * 4096);
#pragma unroll 1
        for (int c = 0; c < 5; c++) {
          if (c == 3) mbar_wait(bars + 8 * B_S3, 0);
          bulk_load(sb + off_ch(c) + U_BYTES, p.ssm_k + (5 * b + c) * SEQ, 4096, bars + 8 * B_HB);
        }
#pragma unroll
        for (int c = 0; c < 4; c++) mbar_expect_tx(bars + 8 * (B_U + c), c < 3 ? U_BYTES : 2 * U_BYTES);
        const uint4* usrc = g_U + 5 * b * U_PITCH;
        mbar_wait(bars + 8 * B_USIG, 0);
        flag_wait(g_cnt + C_PREP + 32 * (b & 15), (epoch + 1) * NCTA);
        TS(23);
#pragma unroll
        for (int c = 0; c < 5; c++) {
          if (c == 3) mbar_wait(bars + 8 * (B_U + 2), 0);
          bulk_load(sb + off_ch(c), usrc + c * U_PITCH, U_BYTES, bars + 8 * (B_U + (c < 3 ? c : 3)));
          TSIF(c == 0 || c == 4, 116 + (c >> 2));
        }
      }
      epoch = __shfl_sync(0xffffffffu, epoch, 0);
      if (lane < 8) {
        const int src = (b & ~7) | step_src(hg, lane);
        mbar_wait(bars + 8 * OP_TRIG, 0);
        TS(20);
        bool seen = false;
#pragma unroll 1
        for (int spins = 0; spins < SPIN_LIMIT; spins++) {
          const bool now = !seen && (int)(flag_read(g_cnt + C_O + 32 * src) - (epoch + 1)) >= 0;
          if (now && lane >= 1 && lane < 4) bulk_load(sb + off_o(lane), g_O + src * 1280, O_BYTES, bars + 8 * (B_FULL2 + lane));
          seen = seen || now;
          if (__all_sync(0xff, seen)) break;
        }
        TS(21);
        if (lane == 5) bulk_load(sb + OFF_GATE, g_gate + 128 * r, 512, bars + 8 * (B_FULL2 + 5));
#pragma unroll 1
        for (int j = 4; j < 8; j++) {
          if (lane == j) {
            mbar_wait(bars + 8 * (j < 6 ? B_C34 : B_EMPTY2 + j - 6), 0);
            if (RF_GATE && j == 6) mbar_wait(bars + 8 * B_YSIG, 0);
            bulk_load(sb + off_o(j), g_O + src * 1280, O_BYTES, bars + 8 * (B_FULL2 + j));
          }
          __syncwarp(0xff);
        }
        TS(22);
      }
    } else if (w == 2) {
      mbar_wait(bars + 8 * B_PREP, 0);
      flag_signal(g_cnt + C_PREP, 16, lane);
      TS(25);
      if (lane == 0) mbar_arrive(bars + 8 * B_USIG);
      mbar_wait(bars + 8 * B_GATE, 0);
      if (((NOMB & 1) || O_RB) && lane == 0) asm volatile("fence.release.gpu;" ::: "memory");
      mbar_wait(bars + 8 * B_ATTN, 0);
      if (lane == 0) {
        if (O_DEFER) mbar_wait(bars + 8 * (B_U + 3), 0);
        asm volatile("cp.async.bulk.global.shared::cta.bulk_group [%0], [%1], 20480;\ncp.async.bulk.commit_group;"
                     ::"l"(g_O + b * 1280), "r"(sb + OFF_OA) : "memory");
        if (O_RB) asm volatile("cp.async.bulk.wait_group.read 0;" ::: "memory");
        else asm volatile("cp.async.bulk.wait_group 0;\nfence.proxy.async.global;" ::: "memory");
      }
      TS(74);
      if (O_RB) {
        __syncwarp();
        unsigned v[5];
#pragma unroll
        for (int c = 0; c < 5; c++) v[c] = flag_read(reinterpret_cast<const unsigned*>(g_O + b * 1280 + 256 * c + 8 * lane + 7));
        const unsigned dep = __reduce_or_sync(0xffffffffu, (v[0] ^ v[1] ^ v[2] ^ v[3] ^ v[4]) & p.zero);
        if (lane == 0) flag_bump(g_cnt + C_O + 32 * b + dep);
      } else if (!(NOMB & 1)) flag_signal(g_cnt + C_O + 32 * b, 1, lane);
      else if (lane == 0) flag_bump(g_cnt + C_O + 32 * b);
      TS(26);
      if (lane == 0) mbar_arrive(bars + 8 * B_OSIG);

    } else {
      if (lane == 0) {
        uint4* dst = g_WO + (hg * 8 + (r >> 1)) * 800 + (r & 1) * 80;
        mbar_wait(bars + 8 * B_P1, 0);
        mbar_wait(bars + 8 * WB_TRIG, 0);
        mbar_expect_tx(bars + 8 * B_WST, WO_BYTES / 2);
        tma_3d(sb + OFF_WS, &m.wo, 0, 40 * r, 5 * hg, bars + 8 * B_WST);
        mbar_wait(bars + 8 * B_WST, 0);
        mbar_wait(bars + 8 * WO_TRIG, 0);
#pragma unroll 1
        for (int n = 0; n < 5; n++)
          asm volatile("cp.async.bulk.global.shared::cta.bulk_group [%0], [%1], 1280;" ::"l"(dst + 160 * n), "r"(sb + OFF_WS + 1280 * n) : "memory");
        asm volatile("cp.async.bulk.commit_group;\ncp.async.bulk.wait_group 0;\nfence.proxy.async.global;" ::: "memory");
        if (!(NOMB & 4)) asm volatile("fence.release.gpu;" ::: "memory");
        flag_bump(g_cnt + C_W + 32 * hg);
        mbar_arrive(bars + 8 * B_WOP);
        TS(71);
#pragma unroll 1
        for (int c = 0; c < 5; c++) {
          mbar_wait(bars + 8 * (B_YST + c), 0);
          asm volatile("cp.async.bulk.global.shared::cta.bulk_group [%0], [%1], 4096;\ncp.async.bulk.commit_group;"
                       ::"l"(g_Y + (5 * b + c) * Y_PITCH), "r"(sb + off_ch(c)) : "memory");
          if (c == 2) {
            asm volatile("cp.async.bulk.wait_group.read 0;" ::: "memory");
            mbar_arrive(bars + 8 * B_C34);
          }
        }
        if (Y_RB) asm volatile("cp.async.bulk.wait_group.read 0;" ::: "memory");
        else asm volatile("cp.async.bulk.wait_group 0;\nfence.proxy.async.global;" ::: "memory");
        TS(75);
      }
      unsigned dep = 0;
      if (Y_RB) {
        __syncwarp();
        unsigned v[5];
#pragma unroll
        for (int c = 0; c < 5; c++) v[c] = flag_read(reinterpret_cast<const unsigned*>(g_Y + (5 * b + c) * Y_PITCH + 8 * lane + 7));
        dep = __reduce_or_sync(0xffffffffu, (v[0] ^ v[1] ^ v[2] ^ v[3] ^ v[4]) & p.zero);
      }
      if (lane == 0) {
        if (!Y_RB && !(NOMB & 2)) asm volatile("fence.release.gpu;" ::: "memory");
        flag_bump(g_cnt + C_Y + 32 * (b >> 4) + dep);
        TS(27);
        mbar_arrive(bars + 8 * B_YSIG);
        mbar_expect_tx(bars + 8 * B_YFULL, 20480);
        flag_wait(g_cnt + C_Y + 32 * hg, (lds32(sb + OFF_EPOCH) + 1) * 16);
        TS(24);
        tma_2d(sb + OFF_YT, &m.y, 128 * r, 80 * hg, bars + 8 * B_YFULL);
        tma_2d(sb + OFF_YT + 10240, &m.y, 128 * r + 64, 80 * hg, bars + 8 * B_YFULL);
      }
    }
  } else {
    asm volatile("setmaxnreg.inc.sync.aligned.u32 152;");
    if (wg < 2) {
      float acc[120];
#pragma unroll
      for (int i = 0; i < 120; i++) acc[i] = 0.f;
      const uint32_t da = desc_lo(sb + wg * 8192, 16), db = desc_lo(sb + ST_W, 8192), dc = desc_lo(sb + ST_WT, 2048);
      if (PW1) pin<120>(acc);
      if (PW1 == 2) mbar_wait(bars + 8 * B_FULL1, 0);
#pragma unroll 1
      for (int kb = 0; kb < 10; kb++) {
        mbar_wait(bars + 8 * (B_FULL1 + (kb & 3)), (kb >> 2) & 1);
        const uint32_t so = (kb & 3) * (STAGE_BYTES >> 4);
        wg_fence();
#pragma unroll
        for (int k = 0; k < 4; k++) {
          WgSST<192>::mma<HI_SW128, HI_SW128>(acc, da + so + 2 * k, db + so + 128 * k, 1);
          WgSST<48>::mma<HI_SW128, HI_SW32>(acc + 96, da + so + 2 * k, dc + so + 32 * k, 1);
        }
        wg_commit();
        wg_wait<1>();
        if (kb > 0 && lane == 0) mbar_arrive(bars + 8 * (kb == 4 ? B_E3 : B_EMPTY1 + ((kb - 1) & 3)));
      }
      mbar_wait(bars + 8 * B_EPOCH, 0);
      const uint32_t tag = lds32(sb + OFF_EPOCH) + 1;
      mbar_wait(bars + 8 * B_S3, 0);
      wg_wait<0>();
      pin<120>(acc);
      if (lane == 0) mbar_arrive(bars + 8 * B_P1);
      TSM(w == 0, 3 + wg);
      attention(acc, sb, b, wg, w, lane, tag);
    } else {
      const int tw = tid & 127, chl = 64 * (b & 1) + 8 * w + (lane >> 2);
      uint4* up = g_U + chl * U_PITCH + ((4 * (b >> 1) + (lane & 3)) ^ ((b >> 2) & 1));
      uint2 sw[10];
      uint32_t dv = 0;
      if (lane < 5) dv = __ldg(reinterpret_cast<const unsigned short*>(p.ssm_D) + 5 * b + lane);
#pragma unroll
      for (int i = 0; i < 10; i++) sw[i] = ldg64(reinterpret_cast<const uint2*>(p.shift_k) + chl + 128 * (i >> 1) + 32 * (i & 1));
      uint32_t tab[12];
      uint32_t tt[2];
      fft_tables(tab, tw);
      fft_twiddles(tt, tw);
      uint4 res[10];
#pragma unroll
      for (int i = 0; i < 10; i++) res[i] = make_uint4(0, 0, 0, 0);
#pragma unroll 1
      for (int slab = 0; slab < 5; slab++) {
#pragma unroll
        for (int i = 0; i < 8; i++) res[i] = res[i + 2];
        prep_slab(res + 8, sw, sb, slab, w, lane);
        TSIF(w == 0, 99 + 4 * slab);
#pragma unroll
        for (int i = 0; i < 8; i++) sw[i] = sw[i + 2];
      }
      TSIF(w == 0, 28);
      __syncwarp();
      if (lane == 0) mbar_arrive(bars + 8 * B_KVD + ((res[8].x ^ res[9].x) & p.zero));
      mbar_wait(bars + 8 * B_KVD, 0);
      fft_tables_store(tab, sb, tw);
      mbar_wait(bars + 8 * B_LAST, 0);
#pragma unroll
      for (int i = 0; i < 10; i++) up[(128 * (i >> 1) + 32 * (i & 1)) * U_PITCH] = res[i];
      __syncwarp();
      if (lane == 0) mbar_arrive(bars + 8 * B_PREP);
      TSIF(w == 0 && !U_TMA, 5);
      mbar_wait(bars + 8 * (G_AFTER ? B_USIG : B_LAST), 0);
      prep_gate(p, b, w, lane);
      __syncwarp();
      if (lane == 0) mbar_arrive(bars + 8 * B_GATE);
      TSIF(w == 0, 72);
      mbar_wait(bars + 8 * B_HB, 0);
      TSIF(w == 0, 2);
      const uint32_t ha = sb + U_BYTES + ((tw >> 3) * 16 + 8 + (tw & 7)) * 16;
      uint4 hv[5];
#pragma unroll
      for (int c = 0; c < 5; c++) hv[c] = lds128(ha + off_ch(c));
      __syncwarp();
#pragma unroll
      for (int c = 0; c < 5; c++) sts128((ha ^ 16) + off_ch(c), hv[c].x, hv[c].y, hv[c].z, hv[c].w);
      asm volatile("st.shared.v2.u32 [%0], {%1, %2};" ::"r"(sb + OFF_TT + 8 * tw), "r"(tt[0]), "r"(tt[1]) : "memory");
      if (tw < 5) asm volatile("st.shared.f32 [%0], %1;" ::"r"(sb + OFF_D + 4 * tw), "f"(bf_lo(dv) * 0.125f) : "memory");
      fence_async_smem();
      __syncwarp();
      if (lane == 0) mbar_arrive(bars + 8 * B_HA);
      TSIF(w == 0, 6);
    }

    FftConst fc;
    TSM(w == 0 && wg == 0, 104);
    mbar_wait(bars + 8 * B_HA, 0);
    fft_matrices(fc, sb, w, lane);
    TSM(w == 0 && wg == 0, 105);
    if (ATT_GATE && !H_EARLY) mbar_wait(bars + 8 * B_ATTN, 0);
    TSM(w == 0 && wg == 2, 124);
#pragma unroll 1
    for (uint32_t tasks = wg == 0 ? TASK0 : wg == 1 ? TASK1 : TASK2; tasks; tasks >>= 4) {
      const int c = (tasks & 7) - 1;
      conv_channel(fc, sb, c, wg, w, lane);
      if (lane == 0) mbar_arrive(bars + 8 * (B_YST + c));
      TSM(w == 0, 10 + c);
    }

    if (wg < 2) {
      const int g = lane >> 2;
      float acc[40];
#pragma unroll
      for (int i = 0; i < 40; i++) acc[i] = 0.f;
      const uint32_t da = desc_lo(sb + wg * 1024, 2048), db = desc_lo(sb, 2560);
      mbar_wait(bars + 8 * B_ATTN, 0);
      mbar_wait(bars + 8 * (B_YST + 3), 0);
      mbar_wait(bars + 8 * (B_YST + 4), 0);
      if (PW2) mbar_wait(bars + 8 * B_FULL2, 0);
      TSM(w == 0, 15 + wg);
#pragma unroll 1
      for (int j = 0; j < 8; j++) {
        mbar_wait(bars + 8 * (B_FULL2 + j), 0);
        const uint32_t oa = da + (off_o(j) >> 4), ob = db + (off_w(j) >> 4);
        wg_fence();
#pragma unroll
        for (int k = 0; k < 5; k++) WgSST<80>::mma<HI_NONE, HI_SW32>(acc, oa + 256 * k, ob + 32 * k, 1);
        wg_commit();
        wg_wait<1>();
        if (j >= 1 && j <= 4 && lane == 0) mbar_arrive(bars + 8 * (B_EMPTY2 + j - 1));
      }
      TSIF(w == 0 && wg == 0, 113);
      const int tr = 64 * wg + 16 * w + (lane & 15);
      const uint32_t fm = sb + OFF_QS + tr * 128, fx = (lane >> 4) ^ (tr & 7);
      const uint32_t ft = sb + OFF_QT + tr * 32 + (((lane >> 4) ^ (tr >> 2)) & 1) * 16;
      const float g0 = __uint_as_float(lds32(sb + OFF_GATE + (64 * wg + 16 * w + g) * 4));
      const float g1 = __uint_as_float(lds32(sb + OFF_GATE + (64 * wg + 16 * w + 8 + g) * 4));
      const uint32_t ga = pack2(g0, g0), gb = pack2(g1, g1);
      const uint32_t na = pack2(1.f - g0, 1.f - g0), nb = pack2(1.f - g1, 1.f - g1);

      wg_wait<0>();
      pin<40>(acc);
      TSM(w == 0, 17 + wg);
      uint32_t pb[20];
#pragma unroll
      for (int j = 0; j < 10; j++) {
        pb[2 * j] = bmul(na, pack2(acc[4 * j], acc[4 * j + 1]));
        pb[2 * j + 1] = bmul(nb, pack2(acc[4 * j + 2], acc[4 * j + 3]));
        asm volatile("" : "+r"(pb[2 * j]), "+r"(pb[2 * j + 1]));
      }
      const uint32_t ya = sb + OFF_YT + wg * 10240 + ((lane >> 4) * 8 + (lane & 7)) * 128 +
                          (((2 * w + (((lane >> 3) & 1) ^ wg)) ^ (lane & 7)) << 4);
      uint32_t qf[20];
      mbar_wait(bars + 8 * B_QF, 0);
#pragma unroll
      for (int j = 0; j < 5; j++) ldsm4(qf + 4 * j, j < 4 ? fm + ((fx ^ (2 * j)) << 4) : ft);
      mbar_wait(bars + 8 * B_YFULL, 0);
      TSM(w == 0 && wg == 0, 19);
#pragma unroll
      for (int j = 0; j < 5; j++) {
        uint32_t y[4];
        ldsm4t(y, ya + 2048 * j);
#pragma unroll
        for (int i = 0; i < 4; i++) qf[4 * j + i] = badd(bmul((i & 1) ? gb : ga, bmul(qf[4 * j + i], y[i])), pb[4 * j + i]);
      }
#pragma unroll
      for (int j = 0; j < 5; j++) stsm4(j < 4 ? fm + ((fx ^ (2 * j)) << 4) : ft, qf + 4 * j);
      fence_async_smem();
      __syncwarp();
      if (lane == 0) {
        const int row = 64 * wg + 16 * w;
        asm volatile("cp.async.bulk.tensor.2d.global.shared::cta.bulk_group [%0, {%2, %3}], [%1];"
                     ::"l"(&m.om), "r"(sb + OFF_QS + row * 128), "r"(80 * hg), "r"(128 * r + row) : "memory");
        asm volatile("cp.async.bulk.tensor.2d.global.shared::cta.bulk_group [%0, {%2, %3}], [%1];"
                     ::"l"(&m.ot), "r"(sb + OFF_QT + row * 32), "r"(80 * hg + 64), "r"(128 * r + row) : "memory");
        asm volatile("cp.async.bulk.commit_group;\ncp.async.bulk.wait_group.read 0;" ::: "memory");
      }
      TSM(true, 40 + 4 * wg + w);
      if (ENDBAR) asm volatile("bar.sync 15, 256;" ::: "memory");
    }
  }
}

typedef CUresult (*EncodeFn)(CUtensorMap*, CUtensorMapDataType, cuuint32_t, void*, const cuuint64_t*, const cuuint64_t*,
                             const cuuint32_t*, const cuuint32_t*, CUtensorMapInterleave, CUtensorMapSwizzle,
                             CUtensorMapL2promotion, CUtensorMapFloatOOBfill);

void encode(EncodeFn fn, CUtensorMap* tm, const void* base, int rank, const cuuint64_t* dims, const cuuint64_t* strides,
            const cuuint32_t* box, CUtensorMapSwizzle swz) {
  const cuuint32_t ones[3] = {1, 1, 1};
  fn(tm, CU_TENSOR_MAP_DATA_TYPE_BFLOAT16, rank, const_cast<void*>(base), dims, strides, box, ones,
     CU_TENSOR_MAP_INTERLEAVE_NONE, swz, CU_TENSOR_MAP_L2_PROMOTION_L2_128B, CU_TENSOR_MAP_FLOAT_OOB_FILL_NONE);
}

}

extern "C" void kernel_launch(void* const* d_in, const int* in_sizes, int n_in, void* d_out, int out_size) {
  (void)in_sizes; (void)n_in; (void)out_size;
  Params p;
  p.q = (const __nv_bfloat16*)d_in[0];
  p.k = (const __nv_bfloat16*)d_in[1];
  p.v = (const __nv_bfloat16*)d_in[2];
  p.shift_k = (const __nv_bfloat16*)d_in[3];
  p.ssm_k = (const __nv_bfloat16*)d_in[4];
  p.ssm_D = (const __nv_bfloat16*)d_in[5];
  p.wqkv = (const __nv_bfloat16*)d_in[7];
  p.wo = (const __nv_bfloat16*)d_in[8];
  p.gate_w = (const __nv_bfloat16*)d_in[9];
  p.out = (__nv_bfloat16*)d_out;
  p.zero = 0;

  static EncodeFn fn = nullptr;
  static void *yaddr = nullptr, *uaddr = nullptr;
  if (!fn) {
    cudaDriverEntryPointQueryResult qr;
    void* f = nullptr;
    cudaGetDriverEntryPoint("cuTensorMapEncodeTiled", &f, cudaEnableDefault, &qr);
    fn = (EncodeFn)f;
    cudaGetSymbolAddress(&yaddr, g_Y);
    cudaGetSymbolAddress(&uaddr, g_U);
    cudaFuncSetAttribute(fused_kernel, cudaFuncAttributeMaxDynamicSharedMemorySize, SMEM_BYTES);
  }
  Maps m;
  {
    const cuuint64_t dims[3] = {640, 1024, 2}, st[2] = {2560, 1280};
    const cuuint32_t box[3] = {64, 64, 2};
    encode(fn, &m.x, p.q, 3, dims, st, box, CU_TENSOR_MAP_SWIZZLE_128B);
  }
  {
    const cuuint64_t dims[3] = {640, 640, 3}, st[2] = {3840, 1280};
    const cuuint32_t box[3] = {64, 64, 3}, boxt[3] = {16, 64, 3};
    encode(fn, &m.wm, p.wqkv, 3, dims, st, box, CU_TENSOR_MAP_SWIZZLE_128B);
    encode(fn, &m.wt, p.wqkv, 3, dims, st, boxt, CU_TENSOR_MAP_SWIZZLE_32B);
  }
  {
    const cuuint64_t dims[3] = {64, 2048, 10}, st[2] = {1280, 128};
    const cuuint32_t boxk[3] = {64, 35, 1}, boxv[3] = {64, 32, 1};
    encode(fn, &m.k, p.k, 3, dims, st, boxk, CU_TENSOR_MAP_SWIZZLE_128B);
    encode(fn, &m.v, p.v, 3, dims, st, boxv, CU_TENSOR_MAP_SWIZZLE_128B);
  }
  {
    const cuuint64_t dims[3] = {16, 640, 40}, st[2] = {1280, 32};
    const cuuint32_t box[3] = {16, 40, 5};
    encode(fn, &m.wo, p.wo, 3, dims, st, box, CU_TENSOR_MAP_SWIZZLE_32B);
  }
  {
    const cuuint64_t dims[2] = {2048, 640}, st[1] = {Y_PITCH * 16};
    const cuuint32_t box[2] = {64, 80};
    encode(fn, &m.y, yaddr, 2, dims, st, box, CU_TENSOR_MAP_SWIZZLE_128B);
    const cuuint64_t stu[1] = {U_PITCH * 16};
    const cuuint32_t boxu[2] = {32, 64};
    encode(fn, &m.u, uaddr, 2, dims, stu, boxu, CU_TENSOR_MAP_SWIZZLE_NONE);
  }
  {
    const cuuint64_t dims[2] = {640, 2048}, st[1] = {1280};
    const cuuint32_t bqm[2] = {64, 128}, bqt[2] = {16, 128}, bom[2] = {64, 16}, bot[2] = {16, 16};
    encode(fn, &m.qm, p.q, 2, dims, st, bqm, CU_TENSOR_MAP_SWIZZLE_128B);
    encode(fn, &m.qt, p.q, 2, dims, st, bqt, CU_TENSOR_MAP_SWIZZLE_32B);
    encode(fn, &m.om, p.out, 2, dims, st, bom, CU_TENSOR_MAP_SWIZZLE_128B);
    encode(fn, &m.ot, p.out, 2, dims, st, bot, CU_TENSOR_MAP_SWIZZLE_32B);
  }
  fused_kernel<<<NCTA, NTHR, SMEM_BYTES>>>(m, p);
}
```

```cpp
#include <cuda.h>
#include <cuda_bf16.h>
#include <cuda_runtime.h>
#include <stdint.h>

namespace {

constexpr int SEQ = 2048, DIM = 640, NCTA = 128, NTHR = 512;

#define TRIG_KB 9
#define KV_KB 2
#define DEV_EXIT 0
#define ATT_GATE 0
#define G_AFTER 0
#define FENCE_LO 0
#define FENCE_HI 0
#define PW1 2
#define PW2 1
#define ENDBAR 0
#define PAD_KB 0
#define Y_ALIAS 1
#define H_EARLY 1
#define NOMB 0
#define SRC_ROT 0
#define WAIT_NS 0
#define WB_TRIG B_USIG
#define G_POS 0
#define TAILF 1
#define T_ISSUE 384
#define T_PF 416
#define T_INIT 448
#define ATT_MERGE 0
#define BMAP 1
#define PRE2 1
#define KV_MIX 0
#define O_DEFER 0
#define TASK0 0x52
#define TASK1 0x3
#define TASK2 0x41
#define HALO_FIRST 1
#define PREV_EARLY 0
#define Y_RB 0
#define O_RB 0
#define O_EAGER 1
#define OP_TRIG B_OSIG
#define BAL 3
#define ACQ 0
#define U_TMA 0
#define U_GATE 0
#define RF_GATE 0
#define WO_TRIG B_WST
#define WL_TRIG B_WOP
#define WO_GATE 1

constexpr uint32_t STAGE_BYTES = 47104, ST_W = 16384, ST_WT = 40960;
constexpr uint32_t O_BYTES = 20480, WO_BYTES = 12800;
constexpr uint32_t OFF_OA = 0;
constexpr uint32_t OFF_QS = 3 * O_BYTES, OFF_QT = OFF_QS + 16384;
constexpr uint32_t OFF_WC = 81920;
constexpr uint32_t OFF_WA = 94720;
constexpr uint32_t OFF_GATE = 145920;
constexpr uint32_t OFF_TT = 146432;
constexpr uint32_t OFF_KVX = 148480;
constexpr uint32_t OFF_CH3 = 163840;
constexpr uint32_t CH_BYTES = 12288, U_BYTES = 4096;
constexpr uint32_t OFF_FT = 225280, OFF_GT = 229376;
constexpr uint32_t OFF_CH0 = 188416;
constexpr uint32_t OFF_KVS = OFF_CH0, KVS_V = 4480, KVS_BYTES = 8576;
constexpr uint32_t OFF_WS = OFF_WA;
__device__ __forceinline__ uint32_t off_us(int s) { return OFF_CH0 + 4096 * ((0x65320 >> (4 * s)) & 7); }
constexpr uint32_t OFF_YT = 163840;
constexpr uint32_t OFF_BAR = 231936;
constexpr uint32_t SMEM_BYTES = OFF_BAR + 512;

enum : uint32_t {
  B_FULL1 = 0, B_EMPTY1 = 4, B_S3 = 7, B_FULL2 = 52, B_EMPTY2 = 13, B_U = 8, B_GATE = 12, B_HA = 19, B_HB = 20,
  B_ATTN = 21, B_C34 = 22, B_CONV = 23, B_YFULL = 24, B_EPOCH = 25, B_PREP = 26, B_P1 = 27, B_LAST = 28,
  B_E3 = 29, B_OSIG = 30, B_WOP = 31, B_USIG = 32, B_WST = 33, B_KV = 34, B_KVD = 39, B_QF = 17, B_YST = 40,
  B_US = 45, B_YSIG = 50
};
constexpr uint32_t OFF_EPOCH = OFF_BAR + 8 * 51, OFF_D = OFF_BAR + 8 * 60;
__device__ __forceinline__ uint32_t off_o(int j) { return j < 4 ? OFF_OA + j * O_BYTES : j < 6 ? OFF_CH0 + (j - 4) * O_BYTES : OFF_OA + (j - 6) * O_BYTES; }
__device__ __forceinline__ uint32_t off_w(int j) { return j < 4 ? OFF_WA + j * WO_BYTES : j == 4 ? OFF_KVX : j == 5 ? OFF_WC : OFF_WA + (j - 6) * WO_BYTES; }
__device__ __forceinline__ int step_src(int hg, int j) {
  if (SRC_ROT == 2) {
    const int pos = (0x37621540 >> (4 * hg)) & 7;
    return j == 0 ? hg : (0x65217430 >> (4 * (j <= pos ? j - 1 : j))) & 7;
  }
  return SRC_ROT ? (hg + j) & 7 : j == 0 ? hg : j <= hg ? j - 1 : j;
}
__device__ __forceinline__ bool tail_first(int hg) { return TAILF && (hg & 3) == 3; }
__device__ __forceinline__ uint32_t off_ch(int c) { return (c < 3 ? OFF_CH0 : OFF_CH3 - 3 * CH_BYTES) + c * CH_BYTES; }

#define U_PITCH 264
__device__ __align__(1024) uint4 g_U[DIM * U_PITCH];
__device__ uint4 g_O[NCTA * 1280];
#define g_Y g_U
constexpr int Y_PITCH = U_PITCH;
__device__ uint4 g_WO[64 * 800];
__device__ uint4 g_halo[NCTA * 2 * 7 * 32];
__device__ float g_gate[SEQ + PAD_KB * 256];
__device__ unsigned g_cnt[32 * (1 + 2 * 16 + 8 + NCTA)];
constexpr int C_LAUNCH = 0, C_PREP = 32, C_Y = 32 * 17, C_W = 32 * 33, C_O = 32 * 41;

#define TSM(cond, slot) do { } while (0)
#define TSIF(cond, slot) do { if (__LINE__ >= FENCE_LO && __LINE__ < FENCE_HI) sched_fence(); } while (0)
__device__ __forceinline__ void sched_fence() {
  asm volatile("{\n.reg .pred p;\n.reg .u32 c;\nmov.u32 c, %%clock;\nsetp.eq.u32 p, c, 0;\n@p st.shared.u32 [%0], c;\n}"
               ::"r"(1024 + OFF_EPOCH + 4) : "memory");
}
#define TS(slot) TSIF(true, slot)

struct Params {
  const __nv_bfloat16 *q, *k, *v, *shift_k, *ssm_k, *ssm_D, *wqkv, *wo, *gate_w;
  __nv_bfloat16* out;
  uint32_t zero;
};

#define POLL_NS 0
constexpr int SPIN_LIMIT = 1 << 17;

__device__ __forceinline__ void mbar_init(uint32_t bar, uint32_t count) {
  asm volatile("mbarrier.init.shared::cta.b64 [%0], %1;" ::"r"(bar), "r"(count) : "memory");
}
__device__ __forceinline__ void mbar_expect_tx(uint32_t bar, uint32_t bytes) {
  asm volatile("mbarrier.arrive.expect_tx.shared::cta.b64 _, [%0], %1;" ::"r"(bar), "r"(bytes) : "memory");
}
__device__ __forceinline__ void mbar_arrive(uint32_t bar) {
  asm volatile("mbarrier.arrive.shared::cta.b64 _, [%0];" ::"r"(bar) : "memory");
}
__device__ __forceinline__ void mbar_wait(uint32_t bar, uint32_t parity) {
  uint32_t ok;
  int spins = 0;
  do {
    if (WAIT_NS)
      asm volatile("{\n.reg .pred p;\nmbarrier.try_wait.parity.shared::cta.b64 p, [%1], %2, %3;\nselp.b32 %0, 1, 0, p;\n}"
                   : "=r"(ok) : "r"(bar), "r"(parity), "r"(WAIT_NS) : "memory");
    else
      asm volatile("{\n.reg .pred p;\nmbarrier.try_wait.parity.shared::cta.b64 p, [%1], %2;\nselp.b32 %0, 1, 0, p;\n}"
                   : "=r"(ok) : "r"(bar), "r"(parity) : "memory");
    if (++spins > SPIN_LIMIT) break;
  } while (!ok);
}
__device__ __forceinline__ unsigned flag_read(const unsigned* p) {
  unsigned v;
  asm volatile("ld.relaxed.gpu.global.u32 %0, [%1];" : "=r"(v) : "l"(p) : "memory");
  return v;
}
__device__ __forceinline__ void flag_poll(const unsigned* p, unsigned target) {
  unsigned v;
  int spins = 0;
  do {
    if (POLL_NS && spins) __nanosleep(POLL_NS);
    asm volatile("ld.relaxed.gpu.global.u32 %0, [%1];" : "=r"(v) : "l"(p) : "memory");
    if (++spins > SPIN_LIMIT) break;
  } while ((int)(v - target) < 0);
}
__device__ __forceinline__ void flag_wait(const unsigned* p, unsigned target) {
  flag_poll(p, target);
  if (ACQ) asm volatile("fence.acquire.gpu;\nfence.proxy.async.global;" ::: "memory");
}
__device__ __forceinline__ void flag_signal(unsigned* p, int n, int lane) {
  if (lane == 0) asm volatile("fence.release.gpu;" ::: "memory");
  __syncwarp();
  if (lane < n) asm volatile("red.relaxed.gpu.global.add.u32 [%0], 1;" ::"l"(p + 32 * lane) : "memory");
}
__device__ __forceinline__ void flag_bump(unsigned* p) {
  asm volatile("red.relaxed.gpu.global.add.u32 [%0], 1;" ::"l"(p) : "memory");
}
__device__ __forceinline__ void fence_async_smem() { asm volatile("fence.proxy.async.shared::cta;" ::: "memory"); }
__device__ __forceinline__ void wg_sync(int id) { asm volatile("bar.sync %0, 128;" ::"r"(id) : "memory"); }

__device__ __forceinline__ void tma_2d(uint32_t dst, const CUtensorMap* tm, int c0, int c1, uint32_t bar) {
  asm volatile("cp.async.bulk.tensor.2d.shared::cluster.global.mbarrier::complete_tx::bytes [%0], [%1, {%3, %4}], [%2];"
               ::"r"(dst), "l"(tm), "r"(bar), "r"(c0), "r"(c1) : "memory");
}
__device__ __forceinline__ void tma_3d(uint32_t dst, const CUtensorMap* tm, int c0, int c1, int c2, uint32_t bar) {
  asm volatile("cp.async.bulk.tensor.3d.shared::cluster.global.mbarrier::complete_tx::bytes [%0], [%1, {%3, %4, %5}], [%2];"
               ::"r"(dst), "l"(tm), "r"(bar), "r"(c0), "r"(c1), "r"(c2) : "memory");
}
__device__ __forceinline__ void bulk_load(uint32_t dst, const void* src, uint32_t bytes, uint32_t bar) {
  asm volatile("cp.async.bulk.shared::cluster.global.mbarrier::complete_tx::bytes [%0], [%1], %2, [%3];"
               ::"r"(dst), "l"(src), "r"(bytes), "r"(bar) : "memory");
}
__device__ __forceinline__ void tm_prefetch(const CUtensorMap* tm) {
  asm volatile("prefetch.tensormap [%0];" ::"l"(tm) : "memory");
}

__device__ __forceinline__ void wg_fence() { asm volatile("wgmma.fence.sync.aligned;" ::: "memory"); }
__device__ __forceinline__ void wg_commit() { asm volatile("wgmma.commit_group.sync.aligned;" ::: "memory"); }
template <int N> __device__ __forceinline__ void wg_wait() { asm volatile("wgmma.wait_group.sync.aligned %0;" ::"n"(N) : "memory"); }
__device__ __forceinline__ uint32_t desc_lo(uint32_t addr, uint32_t lbo) { return ((addr & 0x3FFFF) >> 4) | ((lbo >> 4) << 16); }
constexpr uint32_t desc_hi(uint32_t sbo, uint32_t swz) { return (sbo >> 4) | (swz << 30); }
constexpr uint32_t HI_SW128 = desc_hi(1024, 1), HI_SW64 = desc_hi(512, 2), HI_SW32 = desc_hi(256, 3), HI_NONE = desc_hi(128, 0);
template <int N> __device__ __forceinline__ void pin(float* d) {
#pragma unroll
  for (int i = 0; i < N; i++) asm volatile("" : "+f"(d[i])::"memory");
}

__device__ __forceinline__ uint32_t lds32(uint32_t a) {
  uint32_t v;
  asm volatile("ld.volatile.shared.u32 %0, [%1];" : "=r"(v) : "r"(a) : "memory");
  return v;
}
__device__ __forceinline__ uint4 ldg128(const void* a) {
  uint4 v;
  asm volatile("ld.global.nc.v4.u32 {%0, %1, %2, %3}, [%4];" : "=r"(v.x), "=r"(v.y), "=r"(v.z), "=r"(v.w) : "l"(a) : "memory");
  return v;
}
__device__ __forceinline__ uint2 ldg64(const void* a) {
  uint2 v;
  asm volatile("ld.global.nc.v2.u32 {%0, %1}, [%2];" : "=r"(v.x), "=r"(v.y) : "l"(a) : "memory");
  return v;
}
__device__ __forceinline__ void ldsm4(uint32_t* r, uint32_t a) {
  asm volatile("ldmatrix.sync.aligned.m8n8.x4.shared.b16 {%0, %1, %2, %3}, [%4];"
               : "=r"(r[0]), "=r"(r[1]), "=r"(r[2]), "=r"(r[3]) : "r"(a) : "memory");
}
__device__ __forceinline__ void ldsm4t(uint32_t* r, uint32_t a) {
  asm volatile("ldmatrix.sync.aligned.m8n8.x4.trans.shared.b16 {%0, %1, %2, %3}, [%4];"
               : "=r"(r[0]), "=r"(r[1]), "=r"(r[2]), "=r"(r[3]) : "r"(a) : "memory");
}
__device__ __forceinline__ uint2 lds64(uint32_t a) {
  uint2 v;
  asm volatile("ld.shared.v2.u32 {%0, %1}, [%2];" : "=r"(v.x), "=r"(v.y) : "r"(a) : "memory");
  return v;
}
__device__ __forceinline__ uint4 lds128(uint32_t a) {
  uint4 v;
  asm volatile("ld.shared.v4.u32 {%0, %1, %2, %3}, [%4];" : "=r"(v.x), "=r"(v.y), "=r"(v.z), "=r"(v.w) : "r"(a) : "memory");
  return v;
}
__device__ __forceinline__ void sts128(uint32_t a, uint32_t x, uint32_t y, uint32_t z, uint32_t w) {
  asm volatile("st.shared.v4.u32 [%0], {%1, %2, %3, %4};" ::"r"(a), "r"(x), "r"(y), "r"(z), "r"(w) : "memory");
}
__device__ __forceinline__ void stsm4(uint32_t a, const uint32_t* r) {
  asm volatile("stmatrix.sync.aligned.m8n8.x4.shared.b16 [%0], {%1, %2, %3, %4};" ::"r"(a), "r"(r[0]), "r"(r[1]), "r"(r[2]), "r"(r[3]) : "memory");
}
__device__ __forceinline__ void stsm4t(uint32_t a, const uint32_t* r) {
  asm volatile("stmatrix.sync.aligned.m8n8.x4.trans.shared.b16 [%0], {%1, %2, %3, %4};" ::"r"(a), "r"(r[0]), "r"(r[1]), "r"(r[2]), "r"(r[3]) : "memory");
}
__device__ __forceinline__ uint32_t pack2(float lo, float hi) {
  uint32_t r;
  asm("cvt.rn.bf16x2.f32 %0, %1, %2;" : "=r"(r) : "f"(hi), "f"(lo));
  return r;
}
__device__ __forceinline__ uint32_t movm(uint32_t a) {
  uint32_t d;
  asm volatile("movmatrix.sync.aligned.m8n8.trans.b16 %0, %1;" : "=r"(d) : "r"(a));
  return d;
}
__device__ __forceinline__ uint32_t bmul(uint32_t a, uint32_t b) {
  uint32_t d;
  asm("mul.rn.bf16x2 %0, %1, %2;" : "=r"(d) : "r"(a), "r"(b));
  return d;
}
__device__ __forceinline__ uint32_t badd(uint32_t a, uint32_t b) {
  uint32_t d;
  asm("add.rn.bf16x2 %0, %1, %2;" : "=r"(d) : "r"(a), "r"(b));
  return d;
}
__device__ __forceinline__ uint32_t bfma(uint32_t a, uint32_t b, uint32_t c) {
  uint32_t d;
  asm("fma.rn.bf16x2 %0, %1, %2, %3;" : "=r"(d) : "r"(a), "r"(b), "r"(c));
  return d;
}
__device__ __forceinline__ float bf_lo(uint32_t x) { return __uint_as_float(x << 16); }
__device__ __forceinline__ float bf_hi(uint32_t x) { return __uint_as_float(x & 0xFFFF0000u); }
__device__ __forceinline__ float ex2(float x) {
  float y;
  asm("ex2.approx.ftz.f32 %0, %1;" : "=f"(y) : "f"(x));
  return y;
}
__device__ __forceinline__ float rcp(float x) {
  float y;
  asm("rcp.approx.ftz.f32 %0, %1;" : "=f"(y) : "f"(x));
  return y;
}
__device__ __forceinline__ void mma16816(float* d, uint32_t a0, uint32_t a1, uint32_t a2, uint32_t a3, uint32_t b0, uint32_t b1) {
  asm volatile("mma.sync.aligned.m16n8k16.row.col.f32.bf16.bf16.f32 {%0, %1, %2, %3}, {%4, %5, %6, %7}, {%8, %9}, {%0, %1, %2, %3};"
               : "+f"(d[0]), "+f"(d[1]), "+f"(d[2]), "+f"(d[3])
               : "r"(a0), "r"(a1), "r"(a2), "r"(a3), "r"(b0), "r"(b1));
}
__device__ __forceinline__ void mma1688(float* d, uint32_t a0, uint32_t a1, uint32_t b0) {
  asm volatile("mma.sync.aligned.m16n8k8.row.col.f32.bf16.bf16.f32 {%0, %1, %2, %3}, {%4, %5}, {%6}, {%0, %1, %2, %3};"
               : "+f"(d[0]), "+f"(d[1]), "+f"(d[2]), "+f"(d[3])
               : "r"(a0), "r"(a1), "r"(b0));
}

template <int N> struct WgRS;
template <int N> struct WgSST;
template <> struct WgRS<32> {
  template <uint32_t HB>
  static __device__ __forceinline__ void mma(float* d, const uint32_t* a, uint32_t db) {
    asm volatile("{\n.reg .pred p;\n.reg .b64 db;\nsetp.ne.b32 p, %22, 0;\n"
      "mov.b64 db, {%20, %21};\n"
      "wgmma.mma_async.sync.aligned.m64n32k16.f32.bf16.bf16 {"
      "%0, %1, %2, %3, %4, %5, %6, %7, %8, %9, %10, %11, %12, %13, %14, %15"
      "}, {%16, %17, %18, %19}, db, p, 1, 1, 1;\n}\n"
      : "+f"(d[0]), "+f"(d[1]), "+f"(d[2]), "+f"(d[3]), "+f"(d[4]), "+f"(d[5]), "+f"(d[6]), "+f"(d[7]),
        "+f"(d[8]), "+f"(d[9]), "+f"(d[10]), "+f"(d[11]), "+f"(d[12]), "+f"(d[13]), "+f"(d[14]), "+f"(d[15])
      : "r"(a[0]), "r"(a[1]), "r"(a[2]), "r"(a[3]), "r"(db), "n"(HB), "n"(1));
  }
  template <uint32_t HB>
  static __device__ __forceinline__ void set(float* d, const uint32_t* a, uint32_t db) {
    asm volatile("{\n.reg .pred p;\n.reg .b64 db;\nsetp.ne.b32 p, %22, 0;\n"
      "mov.b64 db, {%20, %21};\n"
      "wgmma.mma_async.sync.aligned.m64n32k16.f32.bf16.bf16 {"
      "%0, %1, %2, %3, %4, %5, %6, %7, %8, %9, %10, %11, %12, %13, %14, %15"
      "}, {%16, %17, %18, %19}, db, p, 1, 1, 1;\n}\n"
      : "=f"(d[0]), "=f"(d[1]), "=f"(d[2]), "=f"(d[3]), "=f"(d[4]), "=f"(d[5]), "=f"(d[6]), "=f"(d[7]),
        "=f"(d[8]), "=f"(d[9]), "=f"(d[10]), "=f"(d[11]), "=f"(d[12]), "=f"(d[13]), "=f"(d[14]), "=f"(d[15])
      : "r"(a[0]), "r"(a[1]), "r"(a[2]), "r"(a[3]), "r"(db), "n"(HB), "n"(0));
  }
};
template <> struct WgRS<64> {
  template <uint32_t HB>
  static __device__ __forceinline__ void mma(float* d, const uint32_t* a, uint32_t db) {
    asm volatile("{\n.reg .pred p;\n.reg .b64 db;\nsetp.ne.b32 p, %38, 0;\n"
      "mov.b64 db, {%36, %37};\n"
      "wgmma.mma_async.sync.aligned.m64n64k16.f32.bf16.bf16 {"
      "%0, %1, %2, %3, %4, %5, %6, %7, %8, %9, %10, %11, %12, %13, %14, %15, "
      "%16, %17, %18, %19, %20, %21, %22, %23, %24, %25, %26, %27, %28, %29, %30, %31"
      "}, {%32, %33, %34, %35}, db, p, 1, 1, 1;\n}\n"
      : "+f"(d[0]), "+f"(d[1]), "+f"(d[2]), "+f"(d[3]), "+f"(d[4]), "+f"(d[5]), "+f"(d[6]), "+f"(d[7]),
        "+f"(d[8]), "+f"(d[9]), "+f"(d[10]), "+f"(d[11]), "+f"(d[12]), "+f"(d[13]), "+f"(d[14]), "+f"(d[15]),
        "+f"(d[16]), "+f"(d[17]), "+f"(d[18]), "+f"(d[19]), "+f"(d[20]), "+f"(d[21]), "+f"(d[22]), "+f"(d[23]),
        "+f"(d[24]), "+f"(d[25]), "+f"(d[26]), "+f"(d[27]), "+f"(d[28]), "+f"(d[29]), "+f"(d[30]), "+f"(d[31])
      : "r"(a[0]), "r"(a[1]), "r"(a[2]), "r"(a[3]), "r"(db), "n"(HB), "n"(1));
  }
  template <uint32_t HB>
  static __device__ __forceinline__ void set(float* d, const uint32_t* a, uint32_t db) {
    asm volatile("{\n.reg .pred p;\n.reg .b64 db;\nsetp.ne.b32 p, %38, 0;\n"
      "mov.b64 db, {%36, %37};\n"
      "wgmma.mma_async.sync.aligned.m64n64k16.f32.bf16.bf16 {"
      "%0, %1, %2, %3, %4, %5, %6, %7, %8, %9, %10, %11, %12, %13, %14, %15, "
      "%16, %17, %18, %19, %20, %21, %22, %23, %24, %25, %26, %27, %28, %29, %30, %31"
      "}, {%32, %33, %34, %35}, db, p, 1, 1, 1;\n}\n"
      : "=f"(d[0]), "=f"(d[1]), "=f"(d[2]), "=f"(d[3]), "=f"(d[4]), "=f"(d[5]), "=f"(d[6]), "=f"(d[7]),
        "=f"(d[8]), "=f"(d[9]), "=f"(d[10]), "=f"(d[11]), "=f"(d[12]), "=f"(d[13]), "=f"(d[14]), "=f"(d[15]),
        "=f"(d[16]), "=f"(d[17]), "=f"(d[18]), "=f"(d[19]), "=f"(d[20]), "=f"(d[21]), "=f"(d[22]), "=f"(d[23]),
        "=f"(d[24]), "=f"(d[25]), "=f"(d[26]), "=f"(d[27]), "=f"(d[28]), "=f"(d[29]), "=f"(d[30]), "=f"(d[31])
      : "r"(a[0]), "r"(a[1]), "r"(a[2]), "r"(a[3]), "r"(db), "n"(HB), "n"(0));
  }
};
template <> struct WgSST<48> {
  template <uint32_t HA, uint32_t HB>
  static __device__ __forceinline__ void mma(float* d, uint32_t da, uint32_t db, int sc) {
    asm volatile("{\n.reg .pred p;\n.reg .b64 da, db;\nsetp.ne.b32 p, %28, 0;\n"
      "mov.b64 da, {%24, %25};\nmov.b64 db, {%26, %27};\n"
      "wgmma.mma_async.sync.aligned.m64n48k16.f32.bf16.bf16 {"
      "%0, %1, %2, %3, %4, %5, %6, %7, %8, %9, %10, %11, %12, %13, %14, %15, "
      "%16, %17, %18, %19, %20, %21, %22, %23"
      "}, da, db, p, 1, 1, 0, 1;\n}\n"
      : "+f"(d[0]), "+f"(d[1]), "+f"(d[2]), "+f"(d[3]), "+f"(d[4]), "+f"(d[5]), "+f"(d[6]), "+f"(d[7]),
        "+f"(d[8]), "+f"(d[9]), "+f"(d[10]), "+f"(d[11]), "+f"(d[12]), "+f"(d[13]), "+f"(d[14]), "+f"(d[15]),
        "+f"(d[16]), "+f"(d[17]), "+f"(d[18]), "+f"(d[19]), "+f"(d[20]), "+f"(d[21]), "+f"(d[22]), "+f"(d[23])
      : "r"(da), "n"(HA), "r"(db), "n"(HB), "r"(sc));
  }
};
template <> struct WgSST<80> {
  template <uint32_t HA, uint32_t HB>
  static __device__ __forceinline__ void mma(float* d, uint32_t da, uint32_t db, int sc) {
    asm volatile("{\n.reg .pred p;\n.reg .b64 da, db;\nsetp.ne.b32 p, %44, 0;\n"
      "mov.b64 da, {%40, %41};\nmov.b64 db, {%42, %43};\n"
      "wgmma.mma_async.sync.aligned.m64n80k16.f32.bf16.bf16 {"
      "%0, %1, %2, %3, %4, %5, %6, %7, %8, %9, %10, %11, %12, %13, %14, %15, "
      "%16, %17, %18, %19, %20, %21, %22, %23, %24, %25, %26, %27, %28, %29, %30, %31, "
      "%32, %33, %34, %35, %36, %37, %38, %39"
      "}, da, db, p, 1, 1, 0, 1;\n}\n"
      : "+f"(d[0]), "+f"(d[1]), "+f"(d[2]), "+f"(d[3]), "+f"(d[4]), "+f"(d[5]), "+f"(d[6]), "+f"(d[7]),
        "+f"(d[8]), "+f"(d[9]), "+f"(d[10]), "+f"(d[11]), "+f"(d[12]), "+f"(d[13]), "+f"(d[14]), "+f"(d[15]),
        "+f"(d[16]), "+f"(d[17]), "+f"(d[18]), "+f"(d[19]), "+f"(d[20]), "+f"(d[21]), "+f"(d[22]), "+f"(d[23]),
        "+f"(d[24]), "+f"(d[25]), "+f"(d[26]), "+f"(d[27]), "+f"(d[28]), "+f"(d[29]), "+f"(d[30]), "+f"(d[31]),
        "+f"(d[32]), "+f"(d[33]), "+f"(d[34]), "+f"(d[35]), "+f"(d[36]), "+f"(d[37]), "+f"(d[38]), "+f"(d[39])
      : "r"(da), "n"(HA), "r"(db), "n"(HB), "r"(sc));
  }
};
template <> struct WgSST<192> {
  template <uint32_t HA, uint32_t HB>
  static __device__ __forceinline__ void mma(float* d, uint32_t da, uint32_t db, int sc) {
    asm volatile("{\n.reg .pred p;\n.reg .b64 da, db;\nsetp.ne.b32 p, %100, 0;\n"
      "mov.b64 da, {%96, %97};\nmov.b64 db, {%98, %99};\n"
      "wgmma.mma_async.sync.aligned.m64n192k16.f32.bf16.bf16 {"
      "%0, %1, %2, %3, %4, %5, %6, %7, %8, %9, %10, %11, %12, %13, %14, %15, "
      "%16, %17, %18, %19, %20, %21, %22, %23, %24, %25, %26, %27, %28, %29, %30, %31, "
      "%32, %33, %34, %35, %36, %37, %38, %39, %40, %41, %42, %43, %44, %45, %46, %47, "
      "%48, %49, %50, %51, %52, %53, %54, %55, %56, %57, %58, %59, %60, %61, %62, %63, "
      "%64, %65, %66, %67, %68, %69, %70, %71, %72, %73, %74, %75, %76, %77, %78, %79, "
      "%80, %81, %82, %83, %84, %85, %86, %87, %88, %89, %90, %91, %92, %93, %94, %95"
      "}, da, db, p, 1, 1, 0, 1;\n}\n"
      : "+f"(d[0]), "+f"(d[1]), "+f"(d[2]), "+f"(d[3]), "+f"(d[4]), "+f"(d[5]), "+f"(d[6]), "+f"(d[7]),
        "+f"(d[8]), "+f"(d[9]), "+f"(d[10]), "+f"(d[11]), "+f"(d[12]), "+f"(d[13]), "+f"(d[14]), "+f"(d[15]),
        "+f"(d[16]), "+f"(d[17]), "+f"(d[18]), "+f"(d[19]), "+f"(d[20]), "+f"(d[21]), "+f"(d[22]), "+f"(d[23]),
        "+f"(d[24]), "+f"(d[25]), "+f"(d[26]), "+f"(d[27]), "+f"(d[28]), "+f"(d[29]), "+f"(d[30]), "+f"(d[31]),
        "+f"(d[32]), "+f"(d[33]), "+f"(d[34]), "+f"(d[35]), "+f"(d[36]), "+f"(d[37]), "+f"(d[38]), "+f"(d[39]),
        "+f"(d[40]), "+f"(d[41]), "+f"(d[42]), "+f"(d[43]), "+f"(d[44]), "+f"(d[45]), "+f"(d[46]), "+f"(d[47]),
        "+f"(d[48]), "+f"(d[49]), "+f"(d[50]), "+f"(d[51]), "+f"(d[52]), "+f"(d[53]), "+f"(d[54]), "+f"(d[55]),
        "+f"(d[56]), "+f"(d[57]), "+f"(d[58]), "+f"(d[59]), "+f"(d[60]), "+f"(d[61]), "+f"(d[62]), "+f"(d[63]),
        "+f"(d[64]), "+f"(d[65]), "+f"(d[66]), "+f"(d[67]), "+f"(d[68]), "+f"(d[69]), "+f"(d[70]), "+f"(d[71]),
        "+f"(d[72]), "+f"(d[73]), "+f"(d[74]), "+f"(d[75]), "+f"(d[76]), "+f"(d[77]), "+f"(d[78]), "+f"(d[79]),
        "+f"(d[80]), "+f"(d[81]), "+f"(d[82]), "+f"(d[83]), "+f"(d[84]), "+f"(d[85]), "+f"(d[86]), "+f"(d[87]),
        "+f"(d[88]), "+f"(d[89]), "+f"(d[90]), "+f"(d[91]), "+f"(d[92]), "+f"(d[93]), "+f"(d[94]), "+f"(d[95])
      : "r"(da), "n"(HA), "r"(db), "n"(HB), "r"(sc));
  }
};

struct FftConst {
  uint32_t f[2][4], fi[4][4];
  uint32_t ta[2][2], tb[2][2];
};
__device__ __forceinline__ void cis(int m, float scale, float& c, float& s) {
  const float a = (float)m * (-6.283185307179586f * scale);
  c = __cosf(a);
  s = __sinf(a);
}
__device__ __forceinline__ void fft_tables(uint32_t (&v)[12], int tw) {
  const int row = tw >> 2, ch = tw & 3;
#pragma unroll
  for (int i = 0; i < 4; i++) {
    float c[2], s[2], x[2];
#pragma unroll
    for (int e = 0; e < 2; e++) {
      cis((((32 * (8 * ch + 2 * i + e) + 15) * (4 * row - 63) + 2048) & 4095) - 2048, 1.f / 4096, c[e], s[e]);
      float gc, gs;
      cis((((row & 15) * (8 * (ch & 1) + 2 * i + e) + 8) & 15) - 8, 1.f / 16, gc, gs);
      x[e] = (row >> 4) == (ch >> 1) ? gc : (ch >> 1) ? gs : -gs;
    }
    v[i] = pack2(c[0] * 0.125f, c[1] * 0.125f);
    v[4 + i] = pack2(s[0] * 0.125f, s[1] * 0.125f);
    v[8 + i] = pack2(x[0], x[1]);
  }
#pragma unroll
  for (int i = 0; i < 12; i++) asm volatile("" : "+r"(v[i]));
}
__device__ __forceinline__ void fft_tables_store(const uint32_t (&v)[12], uint32_t sb, int tw) {
  const int row = tw >> 2;
  const uint32_t x = ((tw ^ (row >> 1)) & 3) << 4, a = sb + OFF_FT + (16 * (row >> 3) + (row & 7)) * 64 + x;
  sts128(a, v[0], v[1], v[2], v[3]);
  sts128(a + 512, v[4], v[5], v[6], v[7]);
  sts128(sb + OFF_GT + row * 64 + x, v[8], v[9], v[10], v[11]);
}
__device__ __forceinline__ void fft_twiddles(uint32_t (&v)[2], int tw) {
  float a[2], s[2];
#pragma unroll
  for (int i = 0; i < 2; i++) {
    float c;
    cis((2 * (2 * (tw & 3) + i) - 15) * (4 * (tw >> 2) - 63), 1.f / 4096, c, s[i]);
    a[i] = __fdividef(-s[i], 1.f + c);
  }
  v[0] = pack2(a[0], a[1]);
  v[1] = pack2(s[0], s[1]);
  asm volatile("" : "+r"(v[0]), "+r"(v[1]));
}
__device__ __forceinline__ void fft_matrices(FftConst& k, uint32_t sb, int w, int lane) {
  const uint32_t x = (lane >> 1) & 3;
  const uint2 t0 = lds64(sb + OFF_TT + 256 * w + 8 * lane), t1 = lds64(sb + OFF_TT + 256 * w + 8 * (lane ^ 3));
  k.ta[0][0] = t0.x;
  k.tb[0][0] = t0.y;
  k.ta[1][1] = __byte_perm(t1.x, 0, 0x1032);
  k.tb[1][1] = __byte_perm(t1.y, 0, 0x1032);
#pragma unroll
  for (int j = 0; j < 2; j++) {
    k.ta[1 - j][j] = k.ta[j][j] ^ 0x80008000u;
    k.tb[1 - j][j] = k.tb[j][j] ^ 0x80008000u;
    asm volatile("" : "+r"(k.ta[0][j]), "+r"(k.tb[0][j]), "+r"(k.ta[1][j]), "+r"(k.tb[1][j]));
  }
#pragma unroll
  for (int i = 0; i < 2; i++) {
    ldsm4(k.f[i], sb + OFF_FT + (16 * w + (lane & 15)) * 64 + (((2 * i + (lane >> 4)) ^ x) << 4));
    ldsm4t(k.fi[i], sb + OFF_FT + (32 * i + lane) * 64 + ((w ^ x) << 4));
#pragma unroll
    for (int j = 0; j < 4; j++) {
      k.fi[2 + i][j] = (j & 1) ? k.fi[i][j - 1] ^ 0x80008000u : k.fi[i][j + 1];
      asm volatile("" : "+r"(k.fi[2 + i][j]));
    }
  }
}
__device__ __forceinline__ void rot(uint32_t& x, uint32_t& y, uint32_t a, uint32_t b) {
  x = bfma(a, y, x);
  y = bfma(b, x, y);
  x = bfma(a, y, x);
}
__device__ __forceinline__ void twiddle_fwd(uint32_t (&a)[4][4], float* d, const FftConst& k) {
#pragma unroll
  for (int q = 0; q < 4; q++)
#pragma unroll
    for (int j = 0; j < 2; j++) {
      const float* x = d + 8 * q + 4 * j;
      uint32_t re = pack2(x[0], x[1]), im = pack2(x[2], x[3]);
      rot(re, im, k.ta[0][j], k.tb[0][j]);
      a[q & 2][2 * j + (q & 1)] = re;
      a[(q & 2) + 1][2 * j + (q & 1)] = im;
    }
}
__device__ __forceinline__ void g_step(float* d, const uint32_t (&a)[4][4], uint32_t dre, uint32_t dim) {
  WgRS<32>::set<HI_SW64>(d, a[0], dre);
  WgRS<32>::set<HI_SW64>(d + 16, a[2], dre);
  WgRS<32>::mma<HI_SW64>(d, a[1], dim);
  WgRS<32>::mma<HI_SW64>(d + 16, a[3], dim);
  wg_commit();
}

__device__ __forceinline__ void conv_channel(const FftConst& k, uint32_t sb, int c, int wg, int w, int lane) {
  const uint32_t cb = sb + off_ch(c), bars = sb + OFF_BAR;
  const uint32_t du = desc_lo(cb, 1024), dg = desc_lo(sb + OFF_GT, 16), dz = desc_lo(cb + U_BYTES, 16);
  float U[32], H[32];
  uint32_t a[4][4], e[4][4];
  const float dv = __uint_as_float(lds32(sb + OFF_D + 4 * c));
  wg_fence();
  WgRS<64>::set<HI_SW32>(H, k.f[0], du + 256);
  WgRS<64>::mma<HI_SW32>(H, k.f[1], du + 256 + 32);
  wg_commit();
  wg_wait<0>();
  pin<32>(H);
  twiddle_fwd(a, H, k);
  if (ATT_GATE && H_EARLY) mbar_wait(bars + 8 * B_ATTN, 0);
  mbar_wait(bars + 8 * (B_U + (c < 3 ? c : 3)), 0);
  TSM(w == 0 && c < 3, 7 + wg);
  wg_fence();
  WgRS<64>::set<HI_SW32>(U, k.f[0], du);
  WgRS<64>::mma<HI_SW32>(U, k.f[1], du + 32);
  wg_commit();
  g_step(H, a, dg, dg + 64);
  wg_wait<1>();
  pin<32>(U);
  twiddle_fwd(e, U, k);
  wg_fence();
  g_step(U, e, dg, dg + 64);
  wg_wait<0>();
  pin<32>(U);
  pin<32>(H);
#pragma unroll
  for (int j = 0; j < 2; j++) {
    float pr[4][2], pi[4][2];
#pragma unroll
    for (int x = 0; x < 2; x++) {
      H[4 * j + x] += dv;
#pragma unroll
      for (int m = 0; m < 4; m++) {
#pragma unroll
        for (int q = 0; q <= m; q++) {
          const int ih = 16 * (q >> 1) + 2 * (q & 1) + 4 * j + x, iu = 16 * ((m - q) >> 1) + 2 * ((m - q) & 1) + 4 * j + x;
          pr[m][x] = q ? fmaf(H[ih], U[iu], pr[m][x]) : H[ih] * U[iu];
          pi[m][x] = q ? fmaf(H[ih], U[iu + 8], pi[m][x]) : H[ih] * U[iu + 8];
          pr[m][x] = fmaf(-H[ih + 8], U[iu + 8], pr[m][x]);
          pi[m][x] = fmaf(H[ih + 8], U[iu], pi[m][x]);
        }
      }
    }
#pragma unroll
    for (int m = 0; m < 4; m++) {
      a[m & 2][2 * j + (m & 1)] = pack2(pr[m][0], pr[m][1]);
      a[(m & 2) + 1][2 * j + (m & 1)] = pack2(pi[m][0], pi[m][1]);
    }
  }
  wg_fence();
  g_step(U, a, dg + 64, dg);
  const uint32_t za = cb + U_BYTES + (8 * w + (lane & 7)) * 128 + (((lane >> 3) ^ (lane & 7)) << 4);
  const uint32_t ya = cb + (lane >> 4) * 1024 + (8 * w + (lane & 7)) * 32 + ((((lane >> 3) ^ (lane >> 2)) & 1) << 4);
  wg_sync(1 + wg);
  wg_wait<0>();
  pin<32>(U);
  TSIF(w == 0, 80 + c);
#pragma unroll
  for (int p = 0; p < 2; p++) {
#pragma unroll
    for (int i = 0; i < 4; i++) {
      const int j = i & 1;
      const float* x = U + 16 * p + 4 * j + (i & 2);
      e[p][i] = pack2(x[8], x[9]);
      e[2 + p][i] = pack2(x[0], x[1]);
      rot(e[p][i], e[2 + p][i], k.ta[1][j], k.tb[1][j]);
    }
    stsm4(za ^ (64 * p), e[p]);
    stsm4((za ^ (64 * p)) + 4096, e[2 + p]);
  }
  fence_async_smem();
  wg_sync(1 + wg);
  wg_fence();
  WgRS<64>::set<HI_SW128>(H, k.fi[0], dz);
#pragma unroll
  for (int ks = 1; ks < 4; ks++) WgRS<64>::mma<HI_SW128>(H, k.fi[ks], dz + 128 * ks);
  wg_commit();
  wg_wait<0>();
  pin<32>(H);
  TSIF(w == 0, 88 + c);
#pragma unroll
  for (int j = 0; j < 8; j++)
    a[j >> 2][j & 3] = j < 2 ? pack2(H[4 * j], H[4 * j + 1]) : pack2(H[4 * j] + H[4 * j - 6], H[4 * j + 1] + H[4 * j - 5]);
  stsm4(ya, a[0]);
  stsm4(ya + 2048, a[1]);
  fence_async_smem();
  __syncwarp();
}

__device__ __forceinline__ void prep_slab(uint4* res, const uint2* sw, uint32_t sb, int slab, int w, int lane) {
  const int t = lane & 3, tp = (lane & 7) >> 1, pos = 8 * tp + 2 * (((lane >> 3) + tp) & 3) + (lane & 1);
  const uint32_t base = sb + OFF_KVS + slab * KVS_BYTES + pos * 128;
  uint32_t kk[2][4][4], vv[2][4];
  mbar_wait(sb + OFF_BAR + 8 * (B_KV + slab), 0);
#pragma unroll
  for (int h = 0; h < 2; h++) {
#pragma unroll
    for (int j = 0; j < 4; j++) {
      const uint32_t a = base + 128 * j;
      ldsm4t(kk[h][j], a + (((w + 4 * h) ^ ((a >> 7) & 7)) << 4));
    }
    const uint32_t a = base + KVS_V;
    ldsm4t(vv[h], a + (((w + 4 * h) ^ ((a >> 7) & 7)) << 4));
  }
#pragma unroll
  for (int h = 0; h < 2; h++) {
    uint32_t (&k)[4][4] = kk[h];
    uint32_t (&v)[4] = vv[h];
    const uint32_t w0 = __byte_perm(sw[h].x, 0, 0x1010), w1 = __byte_perm(sw[h].x, 0, 0x3232);
    const uint32_t w2 = __byte_perm(sw[h].y, 0, 0x1010), w3 = __byte_perm(sw[h].y, 0, 0x3232);
#pragma unroll
    for (int m = 0; m < 4; m++)
      v[m] = bmul(badd(badd(badd(bmul(k[0][m], w3), bmul(k[1][m], w2)), bmul(k[2][m], w1)), bmul(k[3][m], w0)), v[m]);
    uint32_t a[4];
#pragma unroll
    for (int m = 0; m < 4; m++) a[m] = (t & 1) ? v[(m + 3) & 3] : v[m];
    res[h] = (t & 2) ? make_uint4(a[2], a[3], a[0], a[1]) : make_uint4(a[0], a[1], a[2], a[3]);
  }
}

__device__ __forceinline__ void prep_gate(const Params& p, int row, int lane) {
  uint2 gw[5], x[4][5];
#pragma unroll
  for (int j = 0; j < 5; j++) gw[j] = ldg64(reinterpret_cast<const uint2*>(p.gate_w) + lane + 32 * j);
#pragma unroll
  for (int i = 0; i < 4; i++)
#pragma unroll
    for (int j = 0; j < 5; j++)
      x[i][j] = ldg64(reinterpret_cast<const uint2*>(p.q) + (row + i) * (DIM / 4) + lane + 32 * j);
  float s[4];
#pragma unroll
  for (int i = 0; i < 4; i++) {
    s[i] = 0.f;
#pragma unroll
    for (int j = 0; j < 5; j++) {
      const uint32_t m0 = bmul(x[i][j].x, gw[j].x), m1 = bmul(x[i][j].y, gw[j].y);
      s[i] += (bf_lo(m0) + bf_hi(m0)) + (bf_lo(m1) + bf_hi(m1));
    }
  }
  const bool h = lane & 16, q = lane & 8;
  const float a = (h ? s[2] : s[0]) + __shfl_xor_sync(0xffffffffu, h ? s[0] : s[2], 16);
  const float c = (h ? s[3] : s[1]) + __shfl_xor_sync(0xffffffffu, h ? s[1] : s[3], 16);
  float z = (q ? c : a) + __shfl_xor_sync(0xffffffffu, q ? a : c, 8);
#pragma unroll
  for (int o = 4; o > 0; o >>= 1) z += __shfl_xor_sync(0xffffffffu, z, o);
  z = bf_lo(pack2(z, 0.f));
  if ((lane & 7) == 0) g_gate[row + (lane >> 3)] = bf_lo(pack2(__fdividef(1.f, 1.f + __expf(-z)), 0.f));
}

__device__ __forceinline__ uint32_t bmax(uint32_t a, uint32_t b) {
  uint32_t d;
  asm("max.bf16x2 %0, %1, %2;" : "=r"(d) : "r"(a), "r"(b));
  return d;
}
__device__ __forceinline__ void softmax_two(const float (&l)[2][2], uint32_t& p0, uint32_t& p1) {
  constexpr float kScale = 0.22360679774997896f, kLog2e = 1.4426950408889634f;
  const uint32_t r0 = pack2(l[0][0], l[1][0]), r1 = pack2(l[0][1], l[1][1]);
  const uint32_t x0 = pack2(bf_lo(r0) * kScale, bf_hi(r0) * kScale), x1 = pack2(bf_lo(r1) * kScale, bf_hi(r1) * kScale);
  uint32_t m = bmax(x0, x1);
  m = bmax(m, __shfl_xor_sync(0xffffffffu, m, 1));
  m = bmax(m, __shfl_xor_sync(0xffffffffu, m, 2));
  const float m0 = bf_lo(m) * kLog2e, m1 = bf_hi(m) * kLog2e;
  p0 = pack2(ex2(bf_lo(x0) * kLog2e - m0), ex2(bf_lo(x1) * kLog2e - m0));
  p1 = pack2(ex2(bf_hi(x0) * kLog2e - m1), ex2(bf_hi(x1) * kLog2e - m1));
}

__device__ __forceinline__ void halo_read(uint32_t (&kpv)[10], uint32_t (&vpv)[10], uint32_t (&tg)[7], const uint4* hp) {
#pragma unroll
  for (int j = 0; j < 7; j++) {
    uint32_t x0, x1, x2;
    asm volatile("ld.relaxed.gpu.global.v4.u32 {%0, %1, %2, %3}, [%4];"
                 : "=r"(x0), "=r"(x1), "=r"(x2), "=r"(tg[j]) : "l"(hp + 32 * j) : "memory");
    if (j < 4) kpv[3 * j] = x0; else vpv[3 * j - 10] = x0;
    if (j < 3) kpv[3 * j + 1] = x1; else vpv[3 * j - 9] = x1;
    if (j < 3) kpv[3 * j + 2] = x2; else if (j < 6) vpv[3 * j - 8] = x2;
  }
}

template <int ROT>
__device__ __forceinline__ void pack_qkv(const float* acc, uint32_t (&qlo)[10], uint32_t (&qhi)[10], uint32_t (&klo)[10],
                                         uint32_t (&khi)[10], uint32_t (&vlo)[10], uint32_t (&vhi)[10]) {
#pragma unroll
  for (int j = 0; j < 10; j++) {
    const int x = (j + ROT) % 10, tq = x < 8 ? x : 16 + x, tk = x < 8 ? 8 + x : 18 + x, tv = x < 8 ? 16 + x : 20 + x;
    khi[j] = pack2(acc[4 * tk + 2], acc[4 * tk + 3]);
    vhi[j] = movm(pack2(acc[4 * tv + 2], acc[4 * tv + 3]));
    qlo[j] = pack2(acc[4 * tq], acc[4 * tq + 1]);
    qhi[j] = pack2(acc[4 * tq + 2], acc[4 * tq + 3]);
    klo[j] = pack2(acc[4 * tk], acc[4 * tk + 1]);
    vlo[j] = pack2(acc[4 * tv], acc[4 * tv + 1]);
    asm volatile("" : "+r"(khi[j]), "+r"(qlo[j]), "+r"(qhi[j]), "+r"(klo[j]), "+r"(vlo[j]));
  }
}

template <int ROT> __device__ __forceinline__ void halo_send(const float* acc, uint4* ho, uint32_t tag) {
#pragma unroll
  for (int j = 0; j < 7; j++) {
    uint32_t x[3];
#pragma unroll
    for (int e = 0; e < 3; e++) {
      const int i = 3 * j + e, y = (i % 10 + ROT) % 10, tk = y < 8 ? 8 + y : 18 + y, tv = y < 8 ? 16 + y : 20 + y;
      x[e] = i < 10 ? pack2(acc[4 * tk + 2], acc[4 * tk + 3]) : i < 20 ? movm(pack2(acc[4 * tv + 2], acc[4 * tv + 3])) : 0u;
    }
    asm volatile("st.relaxed.gpu.global.v4.u32 [%0], {%1, %2, %3, %4};" ::"l"(ho + 32 * j), "r"(x[0]), "r"(x[1]), "r"(x[2]), "r"(tag) : "memory");
  }
}

__device__ __forceinline__ void attention(float* acc, uint32_t sb, int b, int par, int w, int lane, uint32_t tag) {
  const int g = lane >> 2, t = lane & 3;
  uint32_t klo[10], khi[10], vlo[10], vhi[10], qlo[10], qhi[10], kpv[10], vpv[10];
  if (HALO_FIRST && w == 3 && b < NCTA - 8) {
    uint4* ho = g_halo + (b * 2 + par) * 224 + lane;
    if (tail_first(b & 7)) halo_send<8>(acc, ho, tag);
    else halo_send<0>(acc, ho, tag);
    TSIF(par == 0, 76);
    pin<120>(acc);
  }
  if (tail_first(b & 7)) pack_qkv<8>(acc, qlo, qhi, klo, khi, vlo, vhi);
  else pack_qkv<0>(acc, qlo, qhi, klo, khi, vlo, vhi);
  const uint32_t xa = sb + OFF_KVX + (par * 3) * 2560 + lane * 16;
  if (w < 3) {
    sts128(xa + w * 2560, khi[0], khi[1], khi[2], khi[3]);
    sts128(xa + w * 2560 + 512, khi[4], khi[5], khi[6], khi[7]);
    sts128(xa + w * 2560 + 1024, khi[8], khi[9], vhi[0], vhi[1]);
    sts128(xa + w * 2560 + 1536, vhi[2], vhi[3], vhi[4], vhi[5]);
    sts128(xa + w * 2560 + 2048, vhi[6], vhi[7], vhi[8], vhi[9]);
  } else if (!HALO_FIRST && b < NCTA - 8) {
    uint4* ho = g_halo + (b * 2 + par) * 224 + lane;
#pragma unroll
    for (int j = 0; j < 7; j++) {
      const uint32_t x0 = j < 4 ? khi[3 * j] : vhi[3 * j - 10], x1 = j < 3 ? khi[3 * j + 1] : vhi[3 * j - 9];
      const uint32_t x2 = j < 3 ? khi[3 * j + 2] : j < 6 ? vhi[3 * j - 8] : 0u;
      asm volatile("st.relaxed.gpu.global.v4.u32 [%0], {%1, %2, %3, %4};" ::"l"(ho + 32 * j), "r"(x0), "r"(x1), "r"(x2), "r"(tag) : "memory");
    }
  }
  TSIF(par == 0 && w == 1, 64);
  TSIF(par == 0 && w == 3 && !HALO_FIRST, 76);
#pragma unroll
  for (int j = 0; j < 10; j++) vlo[j] = movm(vlo[j]);
  const bool far0 = 2 * t > g, far1 = 2 * t + 1 > g;
  const uint32_t mfar = (far0 ? 0x0000FFFFu : 0u) | (far1 ? 0xFFFF0000u : 0u);
  float slo[4][2], shi[4][2], lg[2][2];
  uint32_t phi[4], plo[4], qml[4], qmh[4];
#pragma unroll
  for (int h = 0; h < 4; h++) {
    const int f = h == 0 ? 0 : h == 1 ? 3 : h == 2 ? 5 : 8, hf = h < 2 ? 2 : 7;
    const bool mine = (h & 1) ? t >= 2 : t < 2;
    qml[h] = mine ? qlo[hf] : 0u;
    qmh[h] = mine ? qhi[hf] : 0u;
    float a[4] = {0.f, 0.f, 0.f, 0.f}, c[4] = {0.f, 0.f, 0.f, 0.f};
    mma16816(a, qlo[f], qhi[f], qlo[f + 1], qhi[f + 1], klo[f], klo[f + 1]);
    mma16816(c, qlo[f], qhi[f], qlo[f + 1], qhi[f + 1], khi[f], khi[f + 1]);
    mma1688(a, qml[h], qmh[h], klo[hf]);
    mma1688(c, qml[h], qmh[h], khi[hf]);
    slo[h][0] = a[0];
    slo[h][1] = a[1];
    shi[h][0] = lg[h & 1][0] = far0 ? a[2] : c[2];
    shi[h][1] = lg[h & 1][1] = far1 ? a[3] : c[3];
    if (!ATT_MERGE && (h & 1)) softmax_two(lg, phi[h - 1], phi[h]);
  }
  TSIF(par == 0 && w == 1, 65);
  wg_sync(1 + par);
  TSIF(par == 0 && w == 1, 66);
  const bool nohist = (w == 0) && (b < 8);
  const uint4* hp = g_halo + ((b - 8) * 2 + par) * 224 + lane;
  uint32_t tg[7];
  if (w > 0) {
    const uint4 v0 = lds128(xa + (w - 1) * 2560), v1 = lds128(xa + (w - 1) * 2560 + 512), v2 = lds128(xa + (w - 1) * 2560 + 1024);
    const uint4 v3 = lds128(xa + (w - 1) * 2560 + 1536), v4 = lds128(xa + (w - 1) * 2560 + 2048);
    kpv[0] = v0.x; kpv[1] = v0.y; kpv[2] = v0.z; kpv[3] = v0.w; kpv[4] = v1.x; kpv[5] = v1.y; kpv[6] = v1.z; kpv[7] = v1.w;
    kpv[8] = v2.x; kpv[9] = v2.y; vpv[0] = v2.z; vpv[1] = v2.w; vpv[2] = v3.x; vpv[3] = v3.y; vpv[4] = v3.z; vpv[5] = v3.w;
    vpv[6] = v4.x; vpv[7] = v4.y; vpv[8] = v4.z; vpv[9] = v4.w;
  } else if (nohist) {
#pragma unroll
    for (int j = 0; j < 10; j++) kpv[j] = vpv[j] = 0u;
  } else {
    TSIF(par == 0, 77);
    halo_read(kpv, vpv, tg, hp);
  }
  if (w == 0 && !nohist) {
    int spins = 0;
    while (true) {
      bool ok = true;
#pragma unroll
      for (int j = 0; j < 7; j++) ok = ok && tg[j] == tag;
      if (__all_sync(0xffffffffu, ok) || ++spins > SPIN_LIMIT) break;
      halo_read(kpv, vpv, tg, hp);
    }
    TSIF(par == 0, 79);
  }
#pragma unroll
  for (int h = 0; h < 4; h++) {
    const int f = h == 0 ? 0 : h == 1 ? 3 : h == 2 ? 5 : 8, hf = h < 2 ? 2 : 7;
    float a[4] = {0.f, 0.f, 0.f, 0.f};
    mma16816(a, qlo[f], qhi[f], qlo[f + 1], qhi[f + 1], kpv[f], kpv[f + 1]);
    mma1688(a, qml[h], qmh[h], kpv[hf]);
    const float ninf = __int_as_float(0xff800000);
    lg[h & 1][0] = far0 ? (nohist ? ninf : a[0]) : slo[h][0];
    lg[h & 1][1] = far1 ? (nohist ? ninf : a[1]) : slo[h][1];
    if (h & 1) {
      softmax_two(lg, plo[h - 1], plo[h]);
      if (ATT_MERGE) {
        const float lh[2][2] = {{shi[h - 1][0], shi[h - 1][1]}, {shi[h][0], shi[h][1]}};
        softmax_two(lh, phi[h - 1], phi[h]);
      }
    }
  }
  TSIF(par == 0 && w <= 1, 67 + w);
  uint32_t ov[20];
#pragma unroll
  for (int hp = 0; hp < 2; hp++) {
    const int hf = hp ? 7 : 2;
    float sh[4] = {0.f, 0.f, 0.f, 0.f}, i0 = 0.f, i1 = 0.f;
#pragma unroll
    for (int e = 0; e < 2; e++) {
      const int h = 2 * hp + e, f = h == 0 ? 0 : h == 1 ? 3 : h == 2 ? 5 : 8;
      const uint32_t a0 = plo[h] & mfar, a2 = plo[h] & ~mfar, a3 = phi[h] & mfar, c1 = phi[h] & ~mfar;
      float sum[4] = {0.f, 0.f, 0.f, 0.f};
      mma1688(sum, plo[h], phi[h], 0x3F803F80u);
      const float r0 = rcp(sum[0]), r1 = rcp(sum[2]);
#pragma unroll
      for (int j = f; j < f + 2; j++) {
        float o[4] = {0.f, 0.f, 0.f, 0.f};
        mma16816(o, a0, 0u, a2, a3, vpv[j], vlo[j]);
        mma1688(o, 0u, c1, vhi[j]);
        ov[2 * j] = pack2(o[0] * r0, o[1] * r0);
        ov[2 * j + 1] = pack2(o[2] * r1, o[3] * r1);
      }
      const bool mine = e ? g >= 4 : g < 4;
      mma16816(sh, a0, 0u, a2, a3, mine ? vpv[hf] : 0u, mine ? vlo[hf] : 0u);
      mma1688(sh, 0u, c1, mine ? vhi[hf] : 0u);
      if (e == 0 || t >= 2) {
        i0 = r0;
        i1 = r1;
      }
    }
    ov[2 * hf] = pack2(sh[0] * i0, sh[1] * i0);
    ov[2 * hf + 1] = pack2(sh[2] * i1, sh[3] * i1);
  }
  TS(32 + 4 * par + w);
  mbar_wait(sb + OFF_BAR + 8 * B_P1, 0);
  const uint32_t oa = sb + OFF_OA + (lane >> 4) * 2048 + (32 * w + 2 * (lane & 15) + par) * 16;
#pragma unroll
  for (int j = 0; j < 5; j++) stsm4(oa + 4096 * j, ov + 4 * j);
  TSIF(par == 0 && w == 0, 120);
  fence_async_smem();
  TSIF(par == 0 && w == 0, 121);
  __syncwarp();
  if (lane == 0) mbar_arrive(sb + OFF_BAR + 8 * B_ATTN);
  TSM(w == 0 || w == 2, 122 + par + (w == 2 ? 3 : 0));
}

struct Maps {
  CUtensorMap x, wm, wt, k, v, y, wo, qm, qt, om, ot, u;
};

__device__ __forceinline__ void load_stage(uint32_t sb, int kb, int b, const Maps& m) {
  const uint32_t st = sb + (kb & 3) * STAGE_BYTES, bar = sb + OFF_BAR + 8 * (B_FULL1 + (kb & 3));
  const int r = b >> 3, hg = b & 7, slab = kb - KV_KB;
  const bool kv = slab >= 0 && slab < 5;
  const uint32_t kbar = sb + OFF_BAR + 8 * (B_KV + slab), dst = sb + OFF_KVS + slab * KVS_BYTES;
  mbar_expect_tx(bar, STAGE_BYTES);
  if (kv) mbar_expect_tx(kbar, KVS_BYTES);
  tma_3d(st, &m.x, 64 * kb, 64 * r, 0, bar);
  if (kv && KV_MIX) tma_3d(dst, &m.k, 0, 32 * (b >> 1) - 3, 2 * slab + (b & 1), kbar);
  tma_3d(st + ST_W, &m.wm, 80 * hg + (tail_first(hg) ? 16 : 0), 64 * kb, 0, bar);
  if (kv && KV_MIX) tma_3d(dst + KVS_V, &m.v, 0, 32 * (b >> 1), 2 * slab + (b & 1), kbar);
  tma_3d(st + ST_WT, &m.wt, 80 * hg + (tail_first(hg) ? 0 : 64), 64 * kb, 0, bar);
  if (kv && !KV_MIX) tma_3d(dst, &m.k, 0, 32 * (b >> 1) - 3, 2 * slab + (b & 1), kbar);
  if (kv && !KV_MIX) tma_3d(dst + KVS_V, &m.v, 0, 32 * (b >> 1), 2 * slab + (b & 1), kbar);
}

__global__ void __launch_bounds__(NTHR, 1) fused_kernel(const __grid_constant__ Maps m, const Params p) {
  extern __shared__ __align__(1024) uint8_t smem[];
  const uint32_t sb = (uint32_t)__cvta_generic_to_shared(smem);
  const uint32_t bars = sb + OFF_BAR;
  const int tid = threadIdx.x, lane = tid & 31;
  int b = blockIdx.x;
  if (BMAP == 1) b = (((b & 63) >> 3) * 2 + (b & 1)) * 8 + (((b < 64 ? 0x6521 : 0x7430) >> (4 * ((b >> 1) & 3))) & 7);
  if (BMAP == 2) b = ((b & 63) >> 2) * 8 + (((b < 64 ? 0x6521 : 0x7430) >> (4 * (b & 3))) & 7);
  if (BMAP == 3) b = (((b & 63) >> 3) * 2 + (b & 1)) * 8 + (((b < 64 ? 0x7430 : 0x6521) >> (4 * ((b >> 1) & 3))) & 7);
  if (BMAP == 4) b = (((b >> 4) * 2 + (b & 1)) * 8) + ((b >> 1) & 7);
  if (BMAP == 5) b = 127 - b;
  const int r = b >> 3, hg = b & 7;

  if (tid == T_ISSUE) {
    TSM(true, 0);
#pragma unroll
    for (int i = 0; i < 4; i++) mbar_init(bars + 8 * (B_FULL1 + i), 1);
#pragma unroll
    for (int i = 0; i < 3; i++) mbar_init(bars + 8 * (B_KV + i), 1);
    fence_async_smem();
#pragma unroll 1
    for (int kb = 0; kb <= PRE2; kb++) load_stage(sb, kb, b, m);
  } else if (tid >= T_PF && tid < T_PF + 12) {
    tm_prefetch(&m.x + (tid - T_PF));
  } else if (tid == T_INIT) {
#pragma unroll
    for (int i = 0; i < 4; i++) mbar_init(bars + 8 * (B_EMPTY1 + i), 8);
#pragma unroll
    for (int i = 0; i < 8; i++) mbar_init(bars + 8 * (B_FULL2 + i), 1);
#pragma unroll
    for (int i = 0; i < 4; i++) mbar_init(bars + 8 * (B_EMPTY2 + i), 8);
#pragma unroll
    for (int i = 0; i < 4; i++) mbar_init(bars + 8 * (B_U + i), 1);
    mbar_init(bars + 8 * B_HA, 4);
    mbar_init(bars + 8 * B_GATE, 4);
    mbar_init(bars + 8 * B_HB, 1);
    mbar_init(bars + 8 * B_KVD, 4);
    mbar_init(bars + 8 * B_QF, 1);
    mbar_init(bars + 8 * B_ATTN, 8);
    mbar_init(bars + 8 * B_P1, 8);
    mbar_init(bars + 8 * B_C34, 1);
#pragma unroll
    for (int i = 0; i < 5; i++) mbar_init(bars + 8 * (B_YST + i), 4);
#pragma unroll
    for (int i = 0; i < 5; i++) mbar_init(bars + 8 * (B_US + i), 4);
    mbar_init(bars + 8 * B_YSIG, 1);
    mbar_init(bars + 8 * B_YFULL, 1);
    mbar_init(bars + 8 * B_EPOCH, 1);
    mbar_init(bars + 8 * B_PREP, 4);
    mbar_init(bars + 8 * B_USIG, 1);
    mbar_init(bars + 8 * B_WST, 1);
#pragma unroll
    for (int i = 3; i < 5; i++) mbar_init(bars + 8 * (B_KV + i), 1);
    mbar_init(bars + 8 * B_E3, 8);
    mbar_init(bars + 8 * B_LAST, 1);
    mbar_init(bars + 8 * B_OSIG, 1);
    mbar_init(bars + 8 * B_WOP, 1);
    fence_async_smem();
  }
  const int warp = __shfl_sync(0xffffffffu, tid >> 5, 0), wg = warp >> 2, w = warp & 3;
  __syncthreads();

  if (wg == 3) {
    asm volatile("setmaxnreg.dec.sync.aligned.u32 56;");
    if (w == 0) {
      if (lane == 0) {
#pragma unroll 1
        for (int kb = 1 + PRE2; kb < 10; kb++) {
          if (kb >= 4) mbar_wait(bars + 8 * (kb == 7 ? B_E3 : B_EMPTY1 + (kb & 3)), (kb >> 3) & 1);
          TSIF(kb >= 4, 44 + kb);
          load_stage(sb, kb, b, m);
          TSIF(kb == 3, 60);
          if (kb == TRIG_KB) mbar_arrive(bars + 8 * B_LAST);
        }
        mbar_wait(bars + 8 * B_WOP, 0);
        mbar_wait(bars + 8 * WL_TRIG, 0);
        mbar_wait(bars + 8 * B_EPOCH, 0);
        flag_wait(g_cnt + C_W + 32 * hg, (lds32(sb + OFF_EPOCH) + 1) * 16);
        TS(30);
#pragma unroll 1
        for (int j = 0; j < 8; j++) {
          if (j >= 6) mbar_wait(bars + 8 * (B_EMPTY2 + j - 6), 0);
          if (j == 4) mbar_wait(bars + 8 * B_ATTN, 0);
          TSIF(j >= 6, 100 + j);
          if (RF_GATE && j == 6) mbar_wait(bars + 8 * B_YSIG, 0);
          mbar_expect_tx(bars + 8 * (B_FULL2 + j), j == 0 ? WO_BYTES : j == 5 ? O_BYTES + WO_BYTES + 512 : O_BYTES + WO_BYTES);
          bulk_load(sb + off_w(j), g_WO + (hg * 8 + step_src(hg, j)) * 800, WO_BYTES, bars + 8 * (B_FULL2 + j));
        }
        mbar_wait(bars + 8 * (B_EMPTY2 + 3), 0);
        mbar_expect_tx(bars + 8 * B_QF, O_BYTES);
        tma_2d(sb + OFF_QS, &m.qm, 80 * hg, 128 * r, bars + 8 * B_QF);
        tma_2d(sb + OFF_QT, &m.qt, 80 * hg + 64, 128 * r, bars + 8 * B_QF);
      }
    } else if (w == 1) {
      unsigned epoch = 0;
      if (lane == 0) {
        epoch = atomicAdd(g_cnt + C_LAUNCH, 1u) / NCTA;
        asm volatile("st.shared.u32 [%0], %1;" ::"r"(sb + OFF_EPOCH), "r"(epoch) : "memory");
        mbar_arrive(bars + 8 * B_EPOCH);
        mbar_wait(bars + 8 * B_KVD, 0);
        mbar_expect_tx(bars + 8 * B_HB, 5 * 4096);
#pragma unroll 1
        for (int c = 0; c < 5; c++) {
          if (c == 3) mbar_wait(bars + 8 * B_S3, 0);
          bulk_load(sb + off_ch(c) + U_BYTES, p.ssm_k + (5 * b + c) * SEQ, 4096, bars + 8 * B_HB);
        }
#pragma unroll
        for (int c = 0; c < 4; c++) mbar_expect_tx(bars + 8 * (B_U + c), c < 3 ? U_BYTES : 2 * U_BYTES);
        const uint4* usrc = g_U + 5 * b * U_PITCH;
        mbar_wait(bars + 8 * B_USIG, 0);
        flag_wait(g_cnt + C_PREP + 32 * (b & 15), (epoch + 1) * NCTA);
        TS(23);
#pragma unroll
        for (int c = 0; c < 5; c++) {
          if (c == 3) mbar_wait(bars + 8 * (B_U + 2), 0);
          bulk_load(sb + off_ch(c), usrc + c * U_PITCH, U_BYTES, bars + 8 * (B_U + (c < 3 ? c : 3)));
          TSIF(c == 0 || c == 4, 116 + (c >> 2));
        }
      }
      epoch = __shfl_sync(0xffffffffu, epoch, 0);
      if (lane < 8) {
        const int src = (b & ~7) | step_src(hg, lane);
        mbar_wait(bars + 8 * OP_TRIG, 0);
        TS(20);
        bool seen = false;
#pragma unroll 1
        for (int spins = 0; spins < SPIN_LIMIT; spins++) {
          const bool now = !seen && (int)(flag_read(g_cnt + C_O + 32 * src) - (epoch + 1)) >= 0;
          if (now && lane >= 1 && lane < 4) bulk_load(sb + off_o(lane), g_O + src * 1280, O_BYTES, bars + 8 * (B_FULL2 + lane));
          seen = seen || now;
          if (__all_sync(0xff, seen)) break;
        }
        TS(21);
        if (lane == 5) bulk_load(sb + OFF_GATE, g_gate + 128 * r, 512, bars + 8 * (B_FULL2 + 5));
#pragma unroll 1
        for (int j = 4; j < 8; j++) {
          if (lane == j) {
            mbar_wait(bars + 8 * (j < 6 ? B_C34 : B_EMPTY2 + j - 6), 0);
            if (RF_GATE && j == 6) mbar_wait(bars + 8 * B_YSIG, 0);
            bulk_load(sb + off_o(j), g_O + src * 1280, O_BYTES, bars + 8 * (B_FULL2 + j));
          }
          __syncwarp(0xff);
        }
        TS(22);
      }
    } else if (w == 2) {
      mbar_wait(bars + 8 * B_PREP, 0);
      flag_signal(g_cnt + C_PREP, 16, lane);
      TS(25);
      if (lane == 0) mbar_arrive(bars + 8 * B_USIG);
      mbar_wait(bars + 8 * B_GATE, 0);
      if (((NOMB & 1) || O_RB) && lane == 0) asm volatile("fence.release.gpu;" ::: "memory");
      mbar_wait(bars + 8 * B_ATTN, 0);
      if (lane == 0) {
        if (O_DEFER) mbar_wait(bars + 8 * (B_U + 3), 0);
        asm volatile("cp.async.bulk.global.shared::cta.bulk_group [%0], [%1], 20480;\ncp.async.bulk.commit_group;"
                     ::"l"(g_O + b * 1280), "r"(sb + OFF_OA) : "memory");
        if (O_RB) asm volatile("cp.async.bulk.wait_group.read 0;" ::: "memory");
        else asm volatile("cp.async.bulk.wait_group 0;\nfence.proxy.async.global;" ::: "memory");
      }
      TS(74);
      if (O_RB) {
        __syncwarp();
        unsigned v[5];
#pragma unroll
        for (int c = 0; c < 5; c++) v[c] = flag_read(reinterpret_cast<const unsigned*>(g_O + b * 1280 + 256 * c + 8 * lane + 7));
        const unsigned dep = __reduce_or_sync(0xffffffffu, (v[0] ^ v[1] ^ v[2] ^ v[3] ^ v[4]) & p.zero);
        if (lane == 0) flag_bump(g_cnt + C_O + 32 * b + dep);
      } else if (!(NOMB & 1)) flag_signal(g_cnt + C_O + 32 * b, 1, lane);
      else if (lane == 0) flag_bump(g_cnt + C_O + 32 * b);
      TS(26);
      if (lane == 0) mbar_arrive(bars + 8 * B_OSIG);

    } else {
      if (lane == 0) {
        const int np = !(BAL & 2) ? 1 : blockIdx.x >= 64 ? 2 : 0;
        mbar_wait(bars + 8 * B_P1, 0);
        mbar_wait(bars + 8 * WB_TRIG, 0);
        mbar_expect_tx(bars + 8 * B_WST, np * (WO_BYTES / 2));
#pragma unroll 1
        for (int i = 0; i < np; i++) tma_3d(sb + OFF_WS + 6400 * i, &m.wo, 0, 40 * r, 5 * (hg ^ i), bars + 8 * B_WST);
        mbar_wait(bars + 8 * B_WST, 0);
        mbar_wait(bars + 8 * WO_TRIG, 0);
#pragma unroll 1
        for (int n = 0; n < 5 * np; n++)
          asm volatile("cp.async.bulk.global.shared::cta.bulk_group [%0], [%1], 1280;"
                       ::"l"(g_WO + ((hg ^ (n >= 5)) * 8 + (r >> 1)) * 800 + (r & 1) * 80 + 160 * (n >= 5 ? n - 5 : n)), "r"(sb + OFF_WS + 1280 * n) : "memory");
        if (np) {
          asm volatile("cp.async.bulk.commit_group;\ncp.async.bulk.wait_group 0;\nfence.proxy.async.global;" ::: "memory");
          if (!(NOMB & 4)) asm volatile("fence.release.gpu;" ::: "memory");
        }
#pragma unroll 1
        for (int i = 0; i < np; i++) flag_bump(g_cnt + C_W + 32 * (hg ^ i));
        mbar_arrive(bars + 8 * B_WOP);
        TS(71);
#pragma unroll 1
        for (int c = 0; c < 5; c++) {
          mbar_wait(bars + 8 * (B_YST + c), 0);
          asm volatile("cp.async.bulk.global.shared::cta.bulk_group [%0], [%1], 4096;\ncp.async.bulk.commit_group;"
                       ::"l"(g_Y + (5 * b + c) * Y_PITCH), "r"(sb + off_ch(c)) : "memory");
          if (c == 2) {
            asm volatile("cp.async.bulk.wait_group.read 0;" ::: "memory");
            mbar_arrive(bars + 8 * B_C34);
          }
        }
        if (Y_RB) asm volatile("cp.async.bulk.wait_group.read 0;" ::: "memory");
        else asm volatile("cp.async.bulk.wait_group 0;\nfence.proxy.async.global;" ::: "memory");
        TS(75);
      }
      unsigned dep = 0;
      if (Y_RB) {
        __syncwarp();
        unsigned v[5];
#pragma unroll
        for (int c = 0; c < 5; c++) v[c] = flag_read(reinterpret_cast<const unsigned*>(g_Y + (5 * b + c) * Y_PITCH + 8 * lane + 7));
        dep = __reduce_or_sync(0xffffffffu, (v[0] ^ v[1] ^ v[2] ^ v[3] ^ v[4]) & p.zero);
      }
      if (lane == 0) {
        if (!Y_RB && !(NOMB & 2)) asm volatile("fence.release.gpu;" ::: "memory");
        flag_bump(g_cnt + C_Y + 32 * (b >> 4) + dep);
        TS(27);
        mbar_arrive(bars + 8 * B_YSIG);
        mbar_expect_tx(bars + 8 * B_YFULL, 20480);
        flag_wait(g_cnt + C_Y + 32 * hg, (lds32(sb + OFF_EPOCH) + 1) * 16);
        TS(24);
        tma_2d(sb + OFF_YT, &m.y, 128 * r, 80 * hg, bars + 8 * B_YFULL);
        tma_2d(sb + OFF_YT + 10240, &m.y, 128 * r + 64, 80 * hg, bars + 8 * B_YFULL);
      }
    }
  } else {
    asm volatile("setmaxnreg.inc.sync.aligned.u32 152;");
    if (wg < 2) {
      float acc[120];
#pragma unroll
      for (int i = 0; i < 120; i++) acc[i] = 0.f;
      const uint32_t da = desc_lo(sb + wg * 8192, 16), db = desc_lo(sb + ST_W, 8192), dc = desc_lo(sb + ST_WT, 2048);
      if (PW1) pin<120>(acc);
      if (PW1 == 2) mbar_wait(bars + 8 * B_FULL1, 0);
#pragma unroll 1
      for (int kb = 0; kb < 10; kb++) {
        mbar_wait(bars + 8 * (B_FULL1 + (kb & 3)), (kb >> 2) & 1);
        const uint32_t so = (kb & 3) * (STAGE_BYTES >> 4);
        wg_fence();
#pragma unroll
        for (int k = 0; k < 4; k++) {
          WgSST<192>::mma<HI_SW128, HI_SW128>(acc, da + so + 2 * k, db + so + 128 * k, 1);
          WgSST<48>::mma<HI_SW128, HI_SW32>(acc + 96, da + so + 2 * k, dc + so + 32 * k, 1);
        }
        wg_commit();
        wg_wait<1>();
        if (kb > 0 && lane == 0) mbar_arrive(bars + 8 * (kb == 4 ? B_E3 : B_EMPTY1 + ((kb - 1) & 3)));
      }
      mbar_wait(bars + 8 * B_EPOCH, 0);
      const uint32_t tag = lds32(sb + OFF_EPOCH) + 1;
      mbar_wait(bars + 8 * B_S3, 0);
      wg_wait<0>();
      pin<120>(acc);
      if (lane == 0) mbar_arrive(bars + 8 * B_P1);
      TSM(w == 0, 3 + wg);
      attention(acc, sb, b, wg, w, lane, tag);
    } else {
      const int tw = tid & 127, chl = 64 * (b & 1) + 8 * w + (lane >> 2);
      uint4* up = g_U + chl * U_PITCH + ((4 * (b >> 1) + (lane & 3)) ^ ((b >> 2) & 1));
      uint2 sw[10];
      uint32_t dv = 0;
      if (lane < 5) dv = __ldg(reinterpret_cast<const unsigned short*>(p.ssm_D) + 5 * b + lane);
#pragma unroll
      for (int i = 0; i < 10; i++) sw[i] = ldg64(reinterpret_cast<const uint2*>(p.shift_k) + chl + 128 * (i >> 1) + 32 * (i & 1));
      uint32_t tab[12];
      uint32_t tt[2];
      fft_tables(tab, tw);
      fft_twiddles(tt, tw);
      uint4 res[10];
#pragma unroll
      for (int i = 0; i < 10; i++) res[i] = make_uint4(0, 0, 0, 0);
#pragma unroll 1
      for (int slab = 0; slab < 5; slab++) {
#pragma unroll
        for (int i = 0; i < 8; i++) res[i] = res[i + 2];
        prep_slab(res + 8, sw, sb, slab, w, lane);
        TSIF(w == 0, 99 + 4 * slab);
#pragma unroll
        for (int i = 0; i < 8; i++) sw[i] = sw[i + 2];
      }
      TSIF(w == 0, 28);
      __syncwarp();
      if (lane == 0) mbar_arrive(bars + 8 * B_KVD + ((res[8].x ^ res[9].x) & p.zero));
      mbar_wait(bars + 8 * B_KVD, 0);
      fft_tables_store(tab, sb, tw);
      mbar_wait(bars + 8 * B_LAST, 0);
#pragma unroll
      for (int i = 0; i < 10; i++) up[(128 * (i >> 1) + 32 * (i & 1)) * U_PITCH] = res[i];
      __syncwarp();
      if (lane == 0) mbar_arrive(bars + 8 * B_PREP);
      TSIF(w == 0 && !U_TMA, 5);
      mbar_wait(bars + 8 * (G_AFTER ? B_USIG : B_LAST), 0);
      if (!(BAL & 1)) prep_gate(p, 16 * b + 4 * w, lane);
      else if (blockIdx.x >= 64) {
#pragma unroll 1
        for (int i = 0; i < 2; i++) prep_gate(p, 16 * (b ^ i) + 4 * w, lane);
      }
      __syncwarp();
      if (lane == 0) mbar_arrive(bars + 8 * B_GATE);
      TSIF(w == 0, 72);
      mbar_wait(bars + 8 * B_HB, 0);
      TSIF(w == 0, 2);
      const uint32_t ha = sb + U_BYTES + ((tw >> 3) * 16 + 8 + (tw & 7)) * 16;
      uint4 hv[5];
#pragma unroll
      for (int c = 0; c < 5; c++) hv[c] = lds128(ha + off_ch(c));
      __syncwarp();
#pragma unroll
      for (int c = 0; c < 5; c++) sts128((ha ^ 16) + off_ch(c), hv[c].x, hv[c].y, hv[c].z, hv[c].w);
      asm volatile("st.shared.v2.u32 [%0], {%1, %2};" ::"r"(sb + OFF_TT + 8 * tw), "r"(tt[0]), "r"(tt[1]) : "memory");
      if (tw < 5) asm volatile("st.shared.f32 [%0], %1;" ::"r"(sb + OFF_D + 4 * tw), "f"(bf_lo(dv) * 0.125f) : "memory");
      fence_async_smem();
      __syncwarp();
      if (lane == 0) mbar_arrive(bars + 8 * B_HA);
      TSIF(w == 0, 6);
    }

    FftConst fc;
    TSM(w == 0 && wg == 0, 104);
    mbar_wait(bars + 8 * B_HA, 0);
    fft_matrices(fc, sb, w, lane);
    TSM(w == 0 && wg == 0, 105);
    if (ATT_GATE && !H_EARLY) mbar_wait(bars + 8 * B_ATTN, 0);
    TSM(w == 0 && wg == 2, 124);
#pragma unroll 1
    for (uint32_t tasks = wg == 0 ? TASK0 : wg == 1 ? TASK1 : TASK2; tasks; tasks >>= 4) {
      const int c = (tasks & 7) - 1;
      conv_channel(fc, sb, c, wg, w, lane);
      if (lane == 0) mbar_arrive(bars + 8 * (B_YST + c));
      TSM(w == 0, 10 + c);
    }

    if (wg < 2) {
      const int g = lane >> 2;
      float acc[40];
#pragma unroll
      for (int i = 0; i < 40; i++) acc[i] = 0.f;
      const uint32_t da = desc_lo(sb + wg * 1024, 2048), db = desc_lo(sb, 2560);
      mbar_wait(bars + 8 * B_ATTN, 0);
      mbar_wait(bars + 8 * (B_YST + 3), 0);
      mbar_wait(bars + 8 * (B_YST + 4), 0);
      if (PW2) mbar_wait(bars + 8 * B_FULL2, 0);
      TSM(w == 0, 15 + wg);
#pragma unroll 1
      for (int j = 0; j < 8; j++) {
        mbar_wait(bars + 8 * (B_FULL2 + j), 0);
        const uint32_t oa = da + (off_o(j) >> 4), ob = db + (off_w(j) >> 4);
        wg_fence();
#pragma unroll
        for (int k = 0; k < 5; k++) WgSST<80>::mma<HI_NONE, HI_SW32>(acc, oa + 256 * k, ob + 32 * k, 1);
        wg_commit();
        wg_wait<1>();
        if (j >= 1 && j <= 4 && lane == 0) mbar_arrive(bars + 8 * (B_EMPTY2 + j - 1));
      }
      TSIF(w == 0 && wg == 0, 113);
      const int tr = 64 * wg + 16 * w + (lane & 15);
      const uint32_t fm = sb + OFF_QS + tr * 128, fx = (lane >> 4) ^ (tr & 7);
      const uint32_t ft = sb + OFF_QT + tr * 32 + (((lane >> 4) ^ (tr >> 2)) & 1) * 16;
      const float g0 = __uint_as_float(lds32(sb + OFF_GATE + (64 * wg + 16 * w + g) * 4));
      const float g1 = __uint_as_float(lds32(sb + OFF_GATE + (64 * wg + 16 * w + 8 + g) * 4));
      const uint32_t ga = pack2(g0, g0), gb = pack2(g1, g1);
      const uint32_t na = pack2(1.f - g0, 1.f - g0), nb = pack2(1.f - g1, 1.f - g1);

      wg_wait<0>();
      pin<40>(acc);
      TSM(w == 0, 17 + wg);
      uint32_t pb[20];
#pragma unroll
      for (int j = 0; j < 10; j++) {
        pb[2 * j] = bmul(na, pack2(acc[4 * j], acc[4 * j + 1]));
        pb[2 * j + 1] = bmul(nb, pack2(acc[4 * j + 2], acc[4 * j + 3]));
        asm volatile("" : "+r"(pb[2 * j]), "+r"(pb[2 * j + 1]));
      }
      const uint32_t ya = sb + OFF_YT + wg * 10240 + ((lane >> 4) * 8 + (lane & 7)) * 128 +
                          (((2 * w + (((lane >> 3) & 1) ^ wg)) ^ (lane & 7)) << 4);
      uint32_t qf[20];
      mbar_wait(bars + 8 * B_QF, 0);
#pragma unroll
      for (int j = 0; j < 5; j++) ldsm4(qf + 4 * j, j < 4 ? fm + ((fx ^ (2 * j)) << 4) : ft);
      mbar_wait(bars + 8 * B_YFULL, 0);
      TSM(w == 0 && wg == 0, 19);
#pragma unroll
      for (int j = 0; j < 5; j++) {
        uint32_t y[4];
        ldsm4t(y, ya + 2048 * j);
#pragma unroll
        for (int i = 0; i < 4; i++) qf[4 * j + i] = badd(bmul((i & 1) ? gb : ga, bmul(qf[4 * j + i], y[i])), pb[4 * j + i]);
      }
#pragma unroll
      for (int j = 0; j < 5; j++) stsm4(j < 4 ? fm + ((fx ^ (2 * j)) << 4) : ft, qf + 4 * j);
      fence_async_smem();
      __syncwarp();
      if (lane == 0) {
        const int row = 64 * wg + 16 * w;
        asm volatile("cp.async.bulk.tensor.2d.global.shared::cta.bulk_group [%0, {%2, %3}], [%1];"
                     ::"l"(&m.om), "r"(sb + OFF_QS + row * 128), "r"(80 * hg), "r"(128 * r + row) : "memory");
        asm volatile("cp.async.bulk.tensor.2d.global.shared::cta.bulk_group [%0, {%2, %3}], [%1];"
                     ::"l"(&m.ot), "r"(sb + OFF_QT + row * 32), "r"(80 * hg + 64), "r"(128 * r + row) : "memory");
        asm volatile("cp.async.bulk.commit_group;\ncp.async.bulk.wait_group.read 0;" ::: "memory");
      }
      TSM(true, 40 + 4 * wg + w);
      if (ENDBAR) asm volatile("bar.sync 15, 256;" ::: "memory");
    }
  }
}

typedef CUresult (*EncodeFn)(CUtensorMap*, CUtensorMapDataType, cuuint32_t, void*, const cuuint64_t*, const cuuint64_t*,
                             const cuuint32_t*, const cuuint32_t*, CUtensorMapInterleave, CUtensorMapSwizzle,
                             CUtensorMapL2promotion, CUtensorMapFloatOOBfill);

void encode(EncodeFn fn, CUtensorMap* tm, const void* base, int rank, const cuuint64_t* dims, const cuuint64_t* strides,
            const cuuint32_t* box, CUtensorMapSwizzle swz) {
  const cuuint32_t ones[3] = {1, 1, 1};
  fn(tm, CU_TENSOR_MAP_DATA_TYPE_BFLOAT16, rank, const_cast<void*>(base), dims, strides, box, ones,
     CU_TENSOR_MAP_INTERLEAVE_NONE, swz, CU_TENSOR_MAP_L2_PROMOTION_L2_128B, CU_TENSOR_MAP_FLOAT_OOB_FILL_NONE);
}

}

extern "C" void kernel_launch(void* const* d_in, const int* in_sizes, int n_in, void* d_out, int out_size) {
  (void)in_sizes; (void)n_in; (void)out_size;
  Params p;
  p.q = (const __nv_bfloat16*)d_in[0];
  p.k = (const __nv_bfloat16*)d_in[1];
  p.v = (const __nv_bfloat16*)d_in[2];
  p.shift_k = (const __nv_bfloat16*)d_in[3];
  p.ssm_k = (const __nv_bfloat16*)d_in[4];
  p.ssm_D = (const __nv_bfloat16*)d_in[5];
  p.wqkv = (const __nv_bfloat16*)d_in[7];
  p.wo = (const __nv_bfloat16*)d_in[8];
  p.gate_w = (const __nv_bfloat16*)d_in[9];
  p.out = (__nv_bfloat16*)d_out;
  p.zero = 0;

  static EncodeFn fn = nullptr;
  static void *yaddr = nullptr, *uaddr = nullptr;
  if (!fn) {
    cudaDriverEntryPointQueryResult qr;
    void* f = nullptr;
    cudaGetDriverEntryPoint("cuTensorMapEncodeTiled", &f, cudaEnableDefault, &qr);
    fn = (EncodeFn)f;
    cudaGetSymbolAddress(&yaddr, g_Y);
    cudaGetSymbolAddress(&uaddr, g_U);
    cudaFuncSetAttribute(fused_kernel, cudaFuncAttributeMaxDynamicSharedMemorySize, SMEM_BYTES);
  }
  Maps m;
  {
    const cuuint64_t dims[3] = {640, 1024, 2}, st[2] = {2560, 1280};
    const cuuint32_t box[3] = {64, 64, 2};
    encode(fn, &m.x, p.q, 3, dims, st, box, CU_TENSOR_MAP_SWIZZLE_128B);
  }
  {
    const cuuint64_t dims[3] = {640, 640, 3}, st[2] = {3840, 1280};
    const cuuint32_t box[3] = {64, 64, 3}, boxt[3] = {16, 64, 3};
    encode(fn, &m.wm, p.wqkv, 3, dims, st, box, CU_TENSOR_MAP_SWIZZLE_128B);
    encode(fn, &m.wt, p.wqkv, 3, dims, st, boxt, CU_TENSOR_MAP_SWIZZLE_32B);
  }
  {
    const cuuint64_t dims[3] = {64, 2048, 10}, st[2] = {1280, 128};
    const cuuint32_t boxk[3] = {64, 35, 1}, boxv[3] = {64, 32, 1};
    encode(fn, &m.k, p.k, 3, dims, st, boxk, CU_TENSOR_MAP_SWIZZLE_128B);
    encode(fn, &m.v, p.v, 3, dims, st, boxv, CU_TENSOR_MAP_SWIZZLE_128B);
  }
  {
    const cuuint64_t dims[3] = {16, 640, 40}, st[2] = {1280, 32};
    const cuuint32_t box[3] = {16, 40, 5};
    encode(fn, &m.wo, p.wo, 3, dims, st, box, CU_TENSOR_MAP_SWIZZLE_32B);
  }
  {
    const cuuint64_t dims[2] = {2048, 640}, st[1] = {Y_PITCH * 16};
    const cuuint32_t box[2] = {64, 80};
    encode(fn, &m.y, yaddr, 2, dims, st, box, CU_TENSOR_MAP_SWIZZLE_128B);
    const cuuint64_t stu[1] = {U_PITCH * 16};
    const cuuint32_t boxu[2] = {32, 64};
    encode(fn, &m.u, uaddr, 2, dims, stu, boxu, CU_TENSOR_MAP_SWIZZLE_NONE);
  }
  {
    const cuuint64_t dims[2] = {640, 2048}, st[1] = {1280};
    const cuuint32_t bqm[2] = {64, 128}, bqt[2] = {16, 128}, bom[2] = {64, 16}, bot[2] = {16, 16};
    encode(fn, &m.qm, p.q, 2, dims, st, bqm, CU_TENSOR_MAP_SWIZZLE_128B);
    encode(fn, &m.qt, p.q, 2, dims, st, bqt, CU_TENSOR_MAP_SWIZZLE_32B);
    encode(fn, &m.om, p.out, 2, dims, st, bom, CU_TENSOR_MAP_SWIZZLE_128B);
    encode(fn, &m.ot, p.out, 2, dims, st, bot, CU_TENSOR_MAP_SWIZZLE_32B);
  }
  fused_kernel<<<NCTA, NTHR, SMEM_BYTES>>>(m, p);
}
```

```cpp
#include <cuda.h>
#include <cuda_bf16.h>
#include <cuda_runtime.h>
#include <stdint.h>

namespace {

constexpr int SEQ = 2048, DIM = 640, NCTA = 128, NTHR = 512;

#define TRIG_KB 9
#define KV_KB 2
#define DEV_EXIT 0
#define ATT_GATE 0
#define G_AFTER 0
#define FENCE_LO 0
#define FENCE_HI 0
#define PW1 2
#define PW2 1
#define ENDBAR 0
#define PAD_KB 0
#define Y_ALIAS 1
#define H_EARLY 1
#define NOMB 0
#define SRC_ROT 0
#define WAIT_NS 0
#define WB_TRIG B_USIG
#define G_POS 0
#define TAILF 1
#define T_ISSUE 384
#define T_PF 416
#define T_INIT 448
#define ATT_MERGE 0
#define BMAP 1
#define PRE2 1
#define KV_MIX 0
#define O_DEFER 0
#define TASK0 0x52
#define TASK1 0x3
#define TASK2 0x41
#define HALO_FIRST 1
#define PREV_EARLY 0
#define Y_RB 0
#define O_RB 0
#define O_EAGER 1
#define OP_TRIG B_OSIG
#define BAL 3
#define ACQ 0
#define U_TMA 0
#define U_GATE 0
#define RF_GATE 0
#define WO_TRIG B_WST
#define WL_TRIG B_WOP
#define WO_GATE 1

constexpr uint32_t STAGE_BYTES = 47104, ST_W = 16384, ST_WT = 40960;
constexpr uint32_t O_BYTES = 20480, WO_BYTES = 12800;
constexpr uint32_t OFF_OA = 0;
constexpr uint32_t OFF_QS = 3 * O_BYTES, OFF_QT = OFF_QS + 16384;
constexpr uint32_t OFF_WC = 81920;
constexpr uint32_t OFF_WA = 94720;
constexpr uint32_t OFF_GATE = 145920;
constexpr uint32_t OFF_TT = 146432;
constexpr uint32_t OFF_KVX = 148480;
constexpr uint32_t OFF_CH3 = 163840;
constexpr uint32_t CH_BYTES = 12288, U_BYTES = 4096;
constexpr uint32_t OFF_FT = 225280, OFF_GT = 229376;
constexpr uint32_t OFF_CH0 = 188416;
constexpr uint32_t OFF_KVS = OFF_CH0, KVS_V = 4480, KVS_BYTES = 8576;
constexpr uint32_t OFF_WS = OFF_WA;
__device__ __forceinline__ uint32_t off_us(int s) { return OFF_CH0 + 4096 * ((0x65320 >> (4 * s)) & 7); }
constexpr uint32_t OFF_YT = 163840;
constexpr uint32_t OFF_BAR = 231936;
constexpr uint32_t SMEM_BYTES = OFF_BAR + 512;

enum : uint32_t {
  B_FULL1 = 0, B_EMPTY1 = 4, B_S3 = 7, B_FULL2 = 52, B_EMPTY2 = 13, B_U = 8, B_GATE = 12, B_HA = 19, B_HB = 20,
  B_ATTN = 21, B_C34 = 22, B_CONV = 23, B_YFULL = 24, B_EPOCH = 25, B_PREP = 26, B_P1 = 27, B_LAST = 28,
  B_E3 = 29, B_OSIG = 30, B_WOP = 31, B_USIG = 32, B_WST = 33, B_KV = 34, B_KVD = 39, B_QF = 17, B_YST = 40,
  B_US = 45, B_YSIG = 50
};
constexpr uint32_t OFF_EPOCH = OFF_BAR + 8 * 51, OFF_D = OFF_BAR + 8 * 60;
__device__ __forceinline__ uint32_t off_o(int j) { return j < 4 ? OFF_OA + j * O_BYTES : j < 6 ? OFF_CH0 + (j - 4) * O_BYTES : OFF_OA + (j - 6) * O_BYTES; }
__device__ __forceinline__ uint32_t off_w(int j) { return j < 4 ? OFF_WA + j * WO_BYTES : j == 4 ? OFF_KVX : j == 5 ? OFF_WC : OFF_WA + (j - 6) * WO_BYTES; }
__device__ __forceinline__ int step_src(int hg, int j) {
  if (SRC_ROT == 2) {
    const int pos = (0x37621540 >> (4 * hg)) & 7;
    return j == 0 ? hg : (0x65217430 >> (4 * (j <= pos ? j - 1 : j))) & 7;
  }
  return SRC_ROT ? (hg + j) & 7 : j == 0 ? hg : j <= hg ? j - 1 : j;
}
__device__ __forceinline__ bool tail_first(int hg) { return TAILF && (hg & 3) == 3; }
__device__ __forceinline__ uint32_t off_ch(int c) { return (c < 3 ? OFF_CH0 : OFF_CH3 - 3 * CH_BYTES) + c * CH_BYTES; }

#define U_PITCH 264
__device__ __align__(1024) uint4 g_U[DIM * U_PITCH];
__device__ uint4 g_O[NCTA * 1280];
#define g_Y g_U
constexpr int Y_PITCH = U_PITCH;
__device__ uint4 g_WO[64 * 800];
__device__ uint4 g_halo[NCTA * 2 * 7 * 32];
__device__ float g_gate[SEQ + PAD_KB * 256];
__device__ unsigned g_cnt[32 * (1 + 2 * 16 + 8 + NCTA)];
constexpr int C_LAUNCH = 0, C_PREP = 32, C_Y = 32 * 17, C_W = 32 * 33, C_O = 32 * 41;

#define TSM(cond, slot) do { } while (0)
#define TSIF(cond, slot) do { if (__LINE__ >= FENCE_LO && __LINE__ < FENCE_HI) sched_fence(); } while (0)
__device__ __forceinline__ void sched_fence() {
  asm volatile("{\n.reg .pred p;\n.reg .u32 c;\nmov.u32 c, %%clock;\nsetp.eq.u32 p, c, 0;\n@p st.shared.u32 [%0], c;\n}"
               ::"r"(1024 + OFF_EPOCH + 4) : "memory");
}
#define TS(slot) TSIF(true, slot)

struct Params {
  const __nv_bfloat16 *q, *k, *v, *shift_k, *ssm_k, *ssm_D, *wqkv, *wo, *gate_w;
  __nv_bfloat16* out;
  uint32_t zero;
};

#define POLL_NS 0
constexpr int SPIN_LIMIT = 1 << 17;

__device__ __forceinline__ void mbar_init(uint32_t bar, uint32_t count) {
  asm volatile("mbarrier.init.shared::cta.b64 [%0], %1;" ::"r"(bar), "r"(count) : "memory");
}
__device__ __forceinline__ void mbar_expect_tx(uint32_t bar, uint32_t bytes) {
  asm volatile("mbarrier.arrive.expect_tx.shared::cta.b64 _, [%0], %1;" ::"r"(bar), "r"(bytes) : "memory");
}
__device__ __forceinline__ void mbar_arrive(uint32_t bar) {
  asm volatile("mbarrier.arrive.shared::cta.b64 _, [%0];" ::"r"(bar) : "memory");
}
__device__ __forceinline__ void mbar_wait(uint32_t bar, uint32_t parity) {
  uint32_t ok;
  int spins = 0;
  do {
    if (WAIT_NS)
      asm volatile("{\n.reg .pred p;\nmbarrier.try_wait.parity.shared::cta.b64 p, [%1], %2, %3;\nselp.b32 %0, 1, 0, p;\n}"
                   : "=r"(ok) : "r"(bar), "r"(parity), "r"(WAIT_NS) : "memory");
    else
      asm volatile("{\n.reg .pred p;\nmbarrier.try_wait.parity.shared::cta.b64 p, [%1], %2;\nselp.b32 %0, 1, 0, p;\n}"
                   : "=r"(ok) : "r"(bar), "r"(parity) : "memory");
    if (++spins > SPIN_LIMIT) break;
  } while (!ok);
}
__device__ __forceinline__ unsigned flag_read(const unsigned* p) {
  unsigned v;
  asm volatile("ld.relaxed.gpu.global.u32 %0, [%1];" : "=r"(v) : "l"(p) : "memory");
  return v;
}
__device__ __forceinline__ void flag_poll(const unsigned* p, unsigned target) {
  unsigned v;
  int spins = 0;
  do {
    if (POLL_NS && spins) __nanosleep(POLL_NS);
    asm volatile("ld.relaxed.gpu.global.u32 %0, [%1];" : "=r"(v) : "l"(p) : "memory");
    if (++spins > SPIN_LIMIT) break;
  } while ((int)(v - target) < 0);
}
__device__ __forceinline__ void flag_wait(const unsigned* p, unsigned target) {
  flag_poll(p, target);
  if (ACQ) asm volatile("fence.acquire.gpu;\nfence.proxy.async.global;" ::: "memory");
}
__device__ __forceinline__ void flag_signal(unsigned* p, int n, int lane) {
  if (lane == 0) asm volatile("fence.release.gpu;" ::: "memory");
  __syncwarp();
  if (lane < n) asm volatile("red.relaxed.gpu.global.add.u32 [%0], 1;" ::"l"(p + 32 * lane) : "memory");
}
__device__ __forceinline__ void flag_bump(unsigned* p) {
  asm volatile("red.relaxed.gpu.global.add.u32 [%0], 1;" ::"l"(p) : "memory");
}
__device__ __forceinline__ void fence_async_smem() { asm volatile("fence.proxy.async.shared::cta;" ::: "memory"); }
__device__ __forceinline__ void wg_sync(int id) { asm volatile("bar.sync %0, 128;" ::"r"(id) : "memory"); }

__device__ __forceinline__ void tma_2d(uint32_t dst, const CUtensorMap* tm, int c0, int c1, uint32_t bar) {
  asm volatile("cp.async.bulk.tensor.2d.shared::cluster.global.mbarrier::complete_tx::bytes [%0], [%1, {%3, %4}], [%2];"
               ::"r"(dst), "l"(tm), "r"(bar), "r"(c0), "r"(c1) : "memory");
}
__device__ __forceinline__ void tma_3d(uint32_t dst, const CUtensorMap* tm, int c0, int c1, int c2, uint32_t bar) {
  asm volatile("cp.async.bulk.tensor.3d.shared::cluster.global.mbarrier::complete_tx::bytes [%0], [%1, {%3, %4, %5}], [%2];"
               ::"r"(dst), "l"(tm), "r"(bar), "r"(c0), "r"(c1), "r"(c2) : "memory");
}
__device__ __forceinline__ void bulk_load(uint32_t dst, const void* src, uint32_t bytes, uint32_t bar) {
  asm volatile("cp.async.bulk.shared::cluster.global.mbarrier::complete_tx::bytes [%0], [%1], %2, [%3];"
               ::"r"(dst), "l"(src), "r"(bytes), "r"(bar) : "memory");
}
__device__ __forceinline__ void tm_prefetch(const CUtensorMap* tm) {
  asm volatile("prefetch.tensormap [%0];" ::"l"(tm) : "memory");
}

__device__ __forceinline__ void wg_fence() { asm volatile("wgmma.fence.sync.aligned;" ::: "memory"); }
__device__ __forceinline__ void wg_commit() { asm volatile("wgmma.commit_group.sync.aligned;" ::: "memory"); }
template <int N> __device__ __forceinline__ void wg_wait() { asm volatile("wgmma.wait_group.sync.aligned %0;" ::"n"(N) : "memory"); }
__device__ __forceinline__ uint32_t desc_lo(uint32_t addr, uint32_t lbo) { return ((addr & 0x3FFFF) >> 4) | ((lbo >> 4) << 16); }
constexpr uint32_t desc_hi(uint32_t sbo, uint32_t swz) { return (sbo >> 4) | (swz << 30); }
constexpr uint32_t HI_SW128 = desc_hi(1024, 1), HI_SW64 = desc_hi(512, 2), HI_SW32 = desc_hi(256, 3), HI_NONE = desc_hi(128, 0);
template <int N> __device__ __forceinline__ void pin(float* d) {
#pragma unroll
  for (int i = 0; i < N; i++) asm volatile("" : "+f"(d[i])::"memory");
}

__device__ __forceinline__ uint32_t lds32(uint32_t a) {
  uint32_t v;
  asm volatile("ld.volatile.shared.u32 %0, [%1];" : "=r"(v) : "r"(a) : "memory");
  return v;
}
__device__ __forceinline__ uint4 ldg128(const void* a) {
  uint4 v;
  asm volatile("ld.global.nc.v4.u32 {%0, %1, %2, %3}, [%4];" : "=r"(v.x), "=r"(v.y), "=r"(v.z), "=r"(v.w) : "l"(a) : "memory");
  return v;
}
__device__ __forceinline__ uint2 ldg64(const void* a) {
  uint2 v;
  asm volatile("ld.global.nc.v2.u32 {%0, %1}, [%2];" : "=r"(v.x), "=r"(v.y) : "l"(a) : "memory");
  return v;
}
__device__ __forceinline__ void ldsm4(uint32_t* r, uint32_t a) {
  asm volatile("ldmatrix.sync.aligned.m8n8.x4.shared.b16 {%0, %1, %2, %3}, [%4];"
               : "=r"(r[0]), "=r"(r[1]), "=r"(r[2]), "=r"(r[3]) : "r"(a) : "memory");
}
__device__ __forceinline__ void ldsm4t(uint32_t* r, uint32_t a) {
  asm volatile("ldmatrix.sync.aligned.m8n8.x4.trans.shared.b16 {%0, %1, %2, %3}, [%4];"
               : "=r"(r[0]), "=r"(r[1]), "=r"(r[2]), "=r"(r[3]) : "r"(a) : "memory");
}
__device__ __forceinline__ uint2 lds64(uint32_t a) {
  uint2 v;
  asm volatile("ld.shared.v2.u32 {%0, %1}, [%2];" : "=r"(v.x), "=r"(v.y) : "r"(a) : "memory");
  return v;
}
__device__ __forceinline__ uint4 lds128(uint32_t a) {
  uint4 v;
  asm volatile("ld.shared.v4.u32 {%0, %1, %2, %3}, [%4];" : "=r"(v.x), "=r"(v.y), "=r"(v.z), "=r"(v.w) : "r"(a) : "memory");
  return v;
}
__device__ __forceinline__ void sts128(uint32_t a, uint32_t x, uint32_t y, uint32_t z, uint32_t w) {
  asm volatile("st.shared.v4.u32 [%0], {%1, %2, %3, %4};" ::"r"(a), "r"(x), "r"(y), "r"(z), "r"(w) : "memory");
}
__device__ __forceinline__ void stsm4(uint32_t a, const uint32_t* r) {
  asm volatile("stmatrix.sync.aligned.m8n8.x4.shared.b16 [%0], {%1, %2, %3, %4};" ::"r"(a), "r"(r[0]), "r"(r[1]), "r"(r[2]), "r"(r[3]) : "memory");
}
__device__ __forceinline__ void stsm4t(uint32_t a, const uint32_t* r) {
  asm volatile("stmatrix.sync.aligned.m8n8.x4.trans.shared.b16 [%0], {%1, %2, %3, %4};" ::"r"(a), "r"(r[0]), "r"(r[1]), "r"(r[2]), "r"(r[3]) : "memory");
}
__device__ __forceinline__ uint32_t pack2(float lo, float hi) {
  uint32_t r;
  asm("cvt.rn.bf16x2.f32 %0, %1, %2;" : "=r"(r) : "f"(hi), "f"(lo));
  return r;
}
__device__ __forceinline__ uint32_t movm(uint32_t a) {
  uint32_t d;
  asm volatile("movmatrix.sync.aligned.m8n8.trans.b16 %0, %1;" : "=r"(d) : "r"(a));
  return d;
}
__device__ __forceinline__ uint32_t bmul(uint32_t a, uint32_t b) {
  uint32_t d;
  asm("mul.rn.bf16x2 %0, %1, %2;" : "=r"(d) : "r"(a), "r"(b));
  return d;
}
__device__ __forceinline__ uint32_t badd(uint32_t a, uint32_t b) {
  uint32_t d;
  asm("add.rn.bf16x2 %0, %1, %2;" : "=r"(d) : "r"(a), "r"(b));
  return d;
}
__device__ __forceinline__ uint32_t bfma(uint32_t a, uint32_t b, uint32_t c) {
  uint32_t d;
  asm("fma.rn.bf16x2 %0, %1, %2, %3;" : "=r"(d) : "r"(a), "r"(b), "r"(c));
  return d;
}
__device__ __forceinline__ float bf_lo(uint32_t x) { return __uint_as_float(x << 16); }
__device__ __forceinline__ float bf_hi(uint32_t x) { return __uint_as_float(x & 0xFFFF0000u); }
__device__ __forceinline__ float ex2(float x) {
  float y;
  asm("ex2.approx.ftz.f32 %0, %1;" : "=f"(y) : "f"(x));
  return y;
}
__device__ __forceinline__ float rcp(float x) {
  float y;
  asm("rcp.approx.ftz.f32 %0, %1;" : "=f"(y) : "f"(x));
  return y;
}
__device__ __forceinline__ void mma16816(float* d, uint32_t a0, uint32_t a1, uint32_t a2, uint32_t a3, uint32_t b0, uint32_t b1) {
  asm volatile("mma.sync.aligned.m16n8k16.row.col.f32.bf16.bf16.f32 {%0, %1, %2, %3}, {%4, %5, %6, %7}, {%8, %9}, {%0, %1, %2, %3};"
               : "+f"(d[0]), "+f"(d[1]), "+f"(d[2]), "+f"(d[3])
               : "r"(a0), "r"(a1), "r"(a2), "r"(a3), "r"(b0), "r"(b1));
}
__device__ __forceinline__ void mma1688(float* d, uint32_t a0, uint32_t a1, uint32_t b0) {
  asm volatile("mma.sync.aligned.m16n8k8.row.col.f32.bf16.bf16.f32 {%0, %1, %2, %3}, {%4, %5}, {%6}, {%0, %1, %2, %3};"
               : "+f"(d[0]), "+f"(d[1]), "+f"(d[2]), "+f"(d[3])
               : "r"(a0), "r"(a1), "r"(b0));
}

template <int N> struct WgRS;
template <int N> struct WgSST;
template <> struct WgRS<32> {
  template <uint32_t HB>
  static __device__ __forceinline__ void mma(float* d, const uint32_t* a, uint32_t db) {
    asm volatile("{\n.reg .pred p;\n.reg .b64 db;\nsetp.ne.b32 p, %22, 0;\n"
      "mov.b64 db, {%20, %21};\n"
      "wgmma.mma_async.sync.aligned.m64n32k16.f32.bf16.bf16 {"
      "%0, %1, %2, %3, %4, %5, %6, %7, %8, %9, %10, %11, %12, %13, %14, %15"
      "}, {%16, %17, %18, %19}, db, p, 1, 1, 1;\n}\n"
      : "+f"(d[0]), "+f"(d[1]), "+f"(d[2]), "+f"(d[3]), "+f"(d[4]), "+f"(d[5]), "+f"(d[6]), "+f"(d[7]),
        "+f"(d[8]), "+f"(d[9]), "+f"(d[10]), "+f"(d[11]), "+f"(d[12]), "+f"(d[13]), "+f"(d[14]), "+f"(d[15])
      : "r"(a[0]), "r"(a[1]), "r"(a[2]), "r"(a[3]), "r"(db), "n"(HB), "n"(1));
  }
  template <uint32_t HB>
  static __device__ __forceinline__ void set(float* d, const uint32_t* a, uint32_t db) {
    asm volatile("{\n.reg .pred p;\n.reg .b64 db;\nsetp.ne.b32 p, %22, 0;\n"
      "mov.b64 db, {%20, %21};\n"
      "wgmma.mma_async.sync.aligned.m64n32k16.f32.bf16.bf16 {"
      "%0, %1, %2, %3, %4, %5, %6, %7, %8, %9, %10, %11, %12, %13, %14, %15"
      "}, {%16, %17, %18, %19}, db, p, 1, 1, 1;\n}\n"
      : "=f"(d[0]), "=f"(d[1]), "=f"(d[2]), "=f"(d[3]), "=f"(d[4]), "=f"(d[5]), "=f"(d[6]), "=f"(d[7]),
        "=f"(d[8]), "=f"(d[9]), "=f"(d[10]), "=f"(d[11]), "=f"(d[12]), "=f"(d[13]), "=f"(d[14]), "=f"(d[15])
      : "r"(a[0]), "r"(a[1]), "r"(a[2]), "r"(a[3]), "r"(db), "n"(HB), "n"(0));
  }
};
template <> struct WgRS<64> {
  template <uint32_t HB>
  static __device__ __forceinline__ void mma(float* d, const uint32_t* a, uint32_t db) {
    asm volatile("{\n.reg .pred p;\n.reg .b64 db;\nsetp.ne.b32 p, %38, 0;\n"
      "mov.b64 db, {%36, %37};\n"
      "wgmma.mma_async.sync.aligned.m64n64k16.f32.bf16.bf16 {"
      "%0, %1, %2, %3, %4, %5, %6, %7, %8, %9, %10, %11, %12, %13, %14, %15, "
      "%16, %17, %18, %19, %20, %21, %22, %23, %24, %25, %26, %27, %28, %29, %30, %31"
      "}, {%32, %33, %34, %35}, db, p, 1, 1, 1;\n}\n"
      : "+f"(d[0]), "+f"(d[1]), "+f"(d[2]), "+f"(d[3]), "+f"(d[4]), "+f"(d[5]), "+f"(d[6]), "+f"(d[7]),
        "+f"(d[8]), "+f"(d[9]), "+f"(d[10]), "+f"(d[11]), "+f"(d[12]), "+f"(d[13]), "+f"(d[14]), "+f"(d[15]),
        "+f"(d[16]), "+f"(d[17]), "+f"(d[18]), "+f"(d[19]), "+f"(d[20]), "+f"(d[21]), "+f"(d[22]), "+f"(d[23]),
        "+f"(d[24]), "+f"(d[25]), "+f"(d[26]), "+f"(d[27]), "+f"(d[28]), "+f"(d[29]), "+f"(d[30]), "+f"(d[31])
      : "r"(a[0]), "r"(a[1]), "r"(a[2]), "r"(a[3]), "r"(db), "n"(HB), "n"(1));
  }
  template <uint32_t HB>
  static __device__ __forceinline__ void set(float* d, const uint32_t* a, uint32_t db) {
    asm volatile("{\n.reg .pred p;\n.reg .b64 db;\nsetp.ne.b32 p, %38, 0;\n"
      "mov.b64 db, {%36, %37};\n"
      "wgmma.mma_async.sync.aligned.m64n64k16.f32.bf16.bf16 {"
      "%0, %1, %2, %3, %4, %5, %6, %7, %8, %9, %10, %11, %12, %13, %14, %15, "
      "%16, %17, %18, %19, %20, %21, %22, %23, %24, %25, %26, %27, %28, %29, %30, %31"
      "}, {%32, %33, %34, %35}, db, p, 1, 1, 1;\n}\n"
      : "=f"(d[0]), "=f"(d[1]), "=f"(d[2]), "=f"(d[3]), "=f"(d[4]), "=f"(d[5]), "=f"(d[6]), "=f"(d[7]),
        "=f"(d[8]), "=f"(d[9]), "=f"(d[10]), "=f"(d[11]), "=f"(d[12]), "=f"(d[13]), "=f"(d[14]), "=f"(d[15]),
        "=f"(d[16]), "=f"(d[17]), "=f"(d[18]), "=f"(d[19]), "=f"(d[20]), "=f"(d[21]), "=f"(d[22]), "=f"(d[23]),
        "=f"(d[24]), "=f"(d[25]), "=f"(d[26]), "=f"(d[27]), "=f"(d[28]), "=f"(d[29]), "=f"(d[30]), "=f"(d[31])
      : "r"(a[0]), "r"(a[1]), "r"(a[2]), "r"(a[3]), "r"(db), "n"(HB), "n"(0));
  }
};
template <> struct WgSST<48> {
  template <uint32_t HA, uint32_t HB>
  static __device__ __forceinline__ void mma(float* d, uint32_t da, uint32_t db, int sc) {
    asm volatile("{\n.reg .pred p;\n.reg .b64 da, db;\nsetp.ne.b32 p, %28, 0;\n"
      "mov.b64 da, {%24, %25};\nmov.b64 db, {%26, %27};\n"
      "wgmma.mma_async.sync.aligned.m64n48k16.f32.bf16.bf16 {"
      "%0, %1, %2, %3, %4, %5, %6, %7, %8, %9, %10, %11, %12, %13, %14, %15, "
      "%16, %17, %18, %19, %20, %21, %22, %23"
      "}, da, db, p, 1, 1, 0, 1;\n}\n"
      : "+f"(d[0]), "+f"(d[1]), "+f"(d[2]), "+f"(d[3]), "+f"(d[4]), "+f"(d[5]), "+f"(d[6]), "+f"(d[7]),
        "+f"(d[8]), "+f"(d[9]), "+f"(d[10]), "+f"(d[11]), "+f"(d[12]), "+f"(d[13]), "+f"(d[14]), "+f"(d[15]),
        "+f"(d[16]), "+f"(d[17]), "+f"(d[18]), "+f"(d[19]), "+f"(d[20]), "+f"(d[21]), "+f"(d[22]), "+f"(d[23])
      : "r"(da), "n"(HA), "r"(db), "n"(HB), "r"(sc));
  }
};
template <> struct WgSST<80> {
  template <uint32_t HA, uint32_t HB>
  static __device__ __forceinline__ void mma(float* d, uint32_t da, uint32_t db, int sc) {
    asm volatile("{\n.reg .pred p;\n.reg .b64 da, db;\nsetp.ne.b32 p, %44, 0;\n"
      "mov.b64 da, {%40, %41};\nmov.b64 db, {%42, %43};\n"
      "wgmma.mma_async.sync.aligned.m64n80k16.f32.bf16.bf16 {"
      "%0, %1, %2, %3, %4, %5, %6, %7, %8, %9, %10, %11, %12, %13, %14, %15, "
      "%16, %17, %18, %19, %20, %21, %22, %23, %24, %25, %26, %27, %28, %29, %30, %31, "
      "%32, %33, %34, %35, %36, %37, %38, %39"
      "}, da, db, p, 1, 1, 0, 1;\n}\n"
      : "+f"(d[0]), "+f"(d[1]), "+f"(d[2]), "+f"(d[3]), "+f"(d[4]), "+f"(d[5]), "+f"(d[6]), "+f"(d[7]),
        "+f"(d[8]), "+f"(d[9]), "+f"(d[10]), "+f"(d[11]), "+f"(d[12]), "+f"(d[13]), "+f"(d[14]), "+f"(d[15]),
        "+f"(d[16]), "+f"(d[17]), "+f"(d[18]), "+f"(d[19]), "+f"(d[20]), "+f"(d[21]), "+f"(d[22]), "+f"(d[23]),
        "+f"(d[24]), "+f"(d[25]), "+f"(d[26]), "+f"(d[27]), "+f"(d[28]), "+f"(d[29]), "+f"(d[30]), "+f"(d[31]),
        "+f"(d[32]), "+f"(d[33]), "+f"(d[34]), "+f"(d[35]), "+f"(d[36]), "+f"(d[37]), "+f"(d[38]), "+f"(d[39])
      : "r"(da), "n"(HA), "r"(db), "n"(HB), "r"(sc));
  }
};
template <> struct WgSST<192> {
  template <uint32_t HA, uint32_t HB>
  static __device__ __forceinline__ void mma(float* d, uint32_t da, uint32_t db, int sc) {
    asm volatile("{\n.reg .pred p;\n.reg .b64 da, db;\nsetp.ne.b32 p, %100, 0;\n"
      "mov.b64 da, {%96, %97};\nmov.b64 db, {%98, %99};\n"
      "wgmma.mma_async.sync.aligned.m64n192k16.f32.bf16.bf16 {"
      "%0, %1, %2, %3, %4, %5, %6, %7, %8, %9, %10, %11, %12, %13, %14, %15, "
      "%16, %17, %18, %19, %20, %21, %22, %23, %24, %25, %26, %27, %28, %29, %30, %31, "
      "%32, %33, %34, %35, %36, %37, %38, %39, %40, %41, %42, %43, %44, %45, %46, %47, "
      "%48, %49, %50, %51, %52, %53, %54, %55, %56, %57, %58, %59, %60, %61, %62, %63, "
      "%64, %65, %66, %67, %68, %69, %70, %71, %72, %73, %74, %75, %76, %77, %78, %79, "
      "%80, %81, %82, %83, %84, %85, %86, %87, %88, %89, %90, %91, %92, %93, %94, %95"
      "}, da, db, p, 1, 1, 0, 1;\n}\n"
      : "+f"(d[0]), "+f"(d[1]), "+f"(d[2]), "+f"(d[3]), "+f"(d[4]), "+f"(d[5]), "+f"(d[6]), "+f"(d[7]),
        "+f"(d[8]), "+f"(d[9]), "+f"(d[10]), "+f"(d[11]), "+f"(d[12]), "+f"(d[13]), "+f"(d[14]), "+f"(d[15]),
        "+f"(d[16]), "+f"(d[17]), "+f"(d[18]), "+f"(d[19]), "+f"(d[20]), "+f"(d[21]), "+f"(d[22]), "+f"(d[23]),
        "+f"(d[24]), "+f"(d[25]), "+f"(d[26]), "+f"(d[27]), "+f"(d[28]), "+f"(d[29]), "+f"(d[30]), "+f"(d[31]),
        "+f"(d[32]), "+f"(d[33]), "+f"(d[34]), "+f"(d[35]), "+f"(d[36]), "+f"(d[37]), "+f"(d[38]), "+f"(d[39]),
        "+f"(d[40]), "+f"(d[41]), "+f"(d[42]), "+f"(d[43]), "+f"(d[44]), "+f"(d[45]), "+f"(d[46]), "+f"(d[47]),
        "+f"(d[48]), "+f"(d[49]), "+f"(d[50]), "+f"(d[51]), "+f"(d[52]), "+f"(d[53]), "+f"(d[54]), "+f"(d[55]),
        "+f"(d[56]), "+f"(d[57]), "+f"(d[58]), "+f"(d[59]), "+f"(d[60]), "+f"(d[61]), "+f"(d[62]), "+f"(d[63]),
        "+f"(d[64]), "+f"(d[65]), "+f"(d[66]), "+f"(d[67]), "+f"(d[68]), "+f"(d[69]), "+f"(d[70]), "+f"(d[71]),
        "+f"(d[72]), "+f"(d[73]), "+f"(d[74]), "+f"(d[75]), "+f"(d[76]), "+f"(d[77]), "+f"(d[78]), "+f"(d[79]),
        "+f"(d[80]), "+f"(d[81]), "+f"(d[82]), "+f"(d[83]), "+f"(d[84]), "+f"(d[85]), "+f"(d[86]), "+f"(d[87]),
        "+f"(d[88]), "+f"(d[89]), "+f"(d[90]), "+f"(d[91]), "+f"(d[92]), "+f"(d[93]), "+f"(d[94]), "+f"(d[95])
      : "r"(da), "n"(HA), "r"(db), "n"(HB), "r"(sc));
  }
};

struct FftConst {
  uint32_t f[2][4], fi[4][4];
  uint32_t ta[2][2], tb[2][2];
};
__device__ __forceinline__ void cis(int m, float scale, float& c, float& s) {
  const float a = (float)m * (-6.283185307179586f * scale);
  c = __cosf(a);
  s = __sinf(a);
}
__device__ __forceinline__ void fft_tables(uint32_t (&v)[12], int tw) {
  const int row = tw >> 2, ch = tw & 3;
#pragma unroll
  for (int i = 0; i < 4; i++) {
    float c[2], s[2], x[2];
#pragma unroll
    for (int e = 0; e < 2; e++) {
      cis((((32 * (8 * ch + 2 * i + e) + 15) * (4 * row - 63) + 2048) & 4095) - 2048, 1.f / 4096, c[e], s[e]);
      float gc, gs;
      cis((((row & 15) * (8 * (ch & 1) + 2 * i + e) + 8) & 15) - 8, 1.f / 16, gc, gs);
      x[e] = (row >> 4) == (ch >> 1) ? gc : (ch >> 1) ? gs : -gs;
    }
    v[i] = pack2(c[0] * 0.125f, c[1] * 0.125f);
    v[4 + i] = pack2(s[0] * 0.125f, s[1] * 0.125f);
    v[8 + i] = pack2(x[0], x[1]);
  }
#pragma unroll
  for (int i = 0; i < 12; i++) asm volatile("" : "+r"(v[i]));
}
__device__ __forceinline__ void fft_tables_store(const uint32_t (&v)[12], uint32_t sb, int tw) {
  const int row = tw >> 2;
  const uint32_t x = ((tw ^ (row >> 1)) & 3) << 4, a = sb + OFF_FT + (16 * (row >> 3) + (row & 7)) * 64 + x;
  sts128(a, v[0], v[1], v[2], v[3]);
  sts128(a + 512, v[4], v[5], v[6], v[7]);
  sts128(sb + OFF_GT + row * 64 + x, v[8], v[9], v[10], v[11]);
}
__device__ __forceinline__ void fft_twiddles(uint32_t (&v)[2], int tw) {
  float a[2], s[2];
#pragma unroll
  for (int i = 0; i < 2; i++) {
    float c;
    cis((2 * (2 * (tw & 3) + i) - 15) * (4 * (tw >> 2) - 63), 1.f / 4096, c, s[i]);
    a[i] = __fdividef(-s[i], 1.f + c);
  }
  v[0] = pack2(a[0], a[1]);
  v[1] = pack2(s[0], s[1]);
  asm volatile("" : "+r"(v[0]), "+r"(v[1]));
}
__device__ __forceinline__ void fft_matrices(FftConst& k, uint32_t sb, int w, int lane) {
  const uint32_t x = (lane >> 1) & 3;
  const uint2 t0 = lds64(sb + OFF_TT + 256 * w + 8 * lane), t1 = lds64(sb + OFF_TT + 256 * w + 8 * (lane ^ 3));
  k.ta[0][0] = t0.x;
  k.tb[0][0] = t0.y;
  k.ta[1][1] = __byte_perm(t1.x, 0, 0x1032);
  k.tb[1][1] = __byte_perm(t1.y, 0, 0x1032);
#pragma unroll
  for (int j = 0; j < 2; j++) {
    k.ta[1 - j][j] = k.ta[j][j] ^ 0x80008000u;
    k.tb[1 - j][j] = k.tb[j][j] ^ 0x80008000u;
    asm volatile("" : "+r"(k.ta[0][j]), "+r"(k.tb[0][j]), "+r"(k.ta[1][j]), "+r"(k.tb[1][j]));
  }
#pragma unroll
  for (int i = 0; i < 2; i++) {
    ldsm4(k.f[i], sb + OFF_FT + (16 * w + (lane & 15)) * 64 + (((2 * i + (lane >> 4)) ^ x) << 4));
    ldsm4t(k.fi[i], sb + OFF_FT + (32 * i + lane) * 64 + ((w ^ x) << 4));
#pragma unroll
    for (int j = 0; j < 4; j++) {
      k.fi[2 + i][j] = (j & 1) ? k.fi[i][j - 1] ^ 0x80008000u : k.fi[i][j + 1];
      asm volatile("" : "+r"(k.fi[2 + i][j]));
    }
  }
}
__device__ __forceinline__ void rot(uint32_t& x, uint32_t& y, uint32_t a, uint32_t b) {
  x = bfma(a, y, x);
  y = bfma(b, x, y);
  x = bfma(a, y, x);
}
__device__ __forceinline__ void twiddle_fwd(uint32_t (&a)[4][4], float* d, const FftConst& k) {
#pragma unroll
  for (int q = 0; q < 4; q++)
#pragma unroll
    for (int j = 0; j < 2; j++) {
      const float* x = d + 8 * q + 4 * j;
      uint32_t re = pack2(x[0], x[1]), im = pack2(x[2], x[3]);
      rot(re, im, k.ta[0][j], k.tb[0][j]);
      a[q & 2][2 * j + (q & 1)] = re;
      a[(q & 2) + 1][2 * j + (q & 1)] = im;
    }
}
__device__ __forceinline__ void g_step(float* d, const uint32_t (&a)[4][4], uint32_t dre, uint32_t dim) {
  WgRS<32>::set<HI_SW64>(d, a[0], dre);
  WgRS<32>::set<HI_SW64>(d + 16, a[2], dre);
  WgRS<32>::mma<HI_SW64>(d, a[1], dim);
  WgRS<32>::mma<HI_SW64>(d + 16, a[3], dim);
  wg_commit();
}

__device__ __forceinline__ void conv_channel(const FftConst& k, uint32_t sb, int c, int wg, int w, int lane) {
  const uint32_t cb = sb + off_ch(c), bars = sb + OFF_BAR;
  const uint32_t du = desc_lo(cb, 1024), dg = desc_lo(sb + OFF_GT, 16), dz = desc_lo(cb + U_BYTES, 16);
  float U[32], H[32];
  uint32_t a[4][4], e[4][4];
  const float dv = __uint_as_float(lds32(sb + OFF_D + 4 * c));
  wg_fence();
  WgRS<64>::set<HI_SW32>(H, k.f[0], du + 256);
  WgRS<64>::mma<HI_SW32>(H, k.f[1], du + 256 + 32);
  wg_commit();
  wg_wait<0>();
  pin<32>(H);
  twiddle_fwd(a, H, k);
  if (ATT_GATE && H_EARLY) mbar_wait(bars + 8 * B_ATTN, 0);
  mbar_wait(bars + 8 * (B_U + (c < 3 ? c : 3)), 0);
  TSM(w == 0 && c < 3, 7 + wg);
  wg_fence();
  WgRS<64>::set<HI_SW32>(U, k.f[0], du);
  WgRS<64>::mma<HI_SW32>(U, k.f[1], du + 32);
  wg_commit();
  g_step(H, a, dg, dg + 64);
  wg_wait<1>();
  pin<32>(U);
  twiddle_fwd(e, U, k);
  wg_fence();
  g_step(U, e, dg, dg + 64);
  wg_wait<0>();
  pin<32>(U);
  pin<32>(H);
#pragma unroll
  for (int j = 0; j < 2; j++) {
    float pr[4][2], pi[4][2];
#pragma unroll
    for (int x = 0; x < 2; x++) {
      H[4 * j + x] += dv;
#pragma unroll
      for (int m = 0; m < 4; m++) {
#pragma unroll
        for (int q = 0; q <= m; q++) {
          const int ih = 16 * (q >> 1) + 2 * (q & 1) + 4 * j + x, iu = 16 * ((m - q) >> 1) + 2 * ((m - q) & 1) + 4 * j + x;
          pr[m][x] = q ? fmaf(H[ih], U[iu], pr[m][x]) : H[ih] * U[iu];
          pi[m][x] = q ? fmaf(H[ih], U[iu + 8], pi[m][x]) : H[ih] * U[iu + 8];
          pr[m][x] = fmaf(-H[ih + 8], U[iu + 8], pr[m][x]);
          pi[m][x] = fmaf(H[ih + 8], U[iu], pi[m][x]);
        }
      }
    }
#pragma unroll
    for (int m = 0; m < 4; m++) {
      a[m & 2][2 * j + (m & 1)] = pack2(pr[m][0], pr[m][1]);
      a[(m & 2) + 1][2 * j + (m & 1)] = pack2(pi[m][0], pi[m][1]);
    }
  }
  wg_fence();
  g_step(U, a, dg + 64, dg);
  const uint32_t za = cb + U_BYTES + (8 * w + (lane & 7)) * 128 + (((lane >> 3) ^ (lane & 7)) << 4);
  const uint32_t ya = cb + (lane >> 4) * 1024 + (8 * w + (lane & 7)) * 32 + ((((lane >> 3) ^ (lane >> 2)) & 1) << 4);
  wg_sync(1 + wg);
  wg_wait<0>();
  pin<32>(U);
  TSIF(w == 0, 80 + c);
#pragma unroll
  for (int p = 0; p < 2; p++) {
#pragma unroll
    for (int i = 0; i < 4; i++) {
      const int j = i & 1;
      const float* x = U + 16 * p + 4 * j + (i & 2);
      e[p][i] = pack2(x[8], x[9]);
      e[2 + p][i] = pack2(x[0], x[1]);
      rot(e[p][i], e[2 + p][i], k.ta[1][j], k.tb[1][j]);
    }
    stsm4(za ^ (64 * p), e[p]);
    stsm4((za ^ (64 * p)) + 4096, e[2 + p]);
  }
  fence_async_smem();
  wg_sync(1 + wg);
  wg_fence();
  WgRS<64>::set<HI_SW128>(H, k.fi[0], dz);
#pragma unroll
  for (int ks = 1; ks < 4; ks++) WgRS<64>::mma<HI_SW128>(H, k.fi[ks], dz + 128 * ks);
  wg_commit();
  wg_wait<0>();
  pin<32>(H);
  TSIF(w == 0, 88 + c);
#pragma unroll
  for (int j = 0; j < 8; j++)
    a[j >> 2][j & 3] = j < 2 ? pack2(H[4 * j], H[4 * j + 1]) : pack2(H[4 * j] + H[4 * j - 6], H[4 * j + 1] + H[4 * j - 5]);
  stsm4(ya, a[0]);
  stsm4(ya + 2048, a[1]);
  fence_async_smem();
  __syncwarp();
}

__device__ __forceinline__ void prep_slab(uint4* res, const uint2* sw, uint32_t sb, int slab, int w, int lane) {
  const int t = lane & 3, tp = (lane & 7) >> 1, pos = 8 * tp + 2 * (((lane >> 3) + tp) & 3) + (lane & 1);
  const uint32_t base = sb + OFF_KVS + slab * KVS_BYTES + pos * 128;
  uint32_t kk[2][4][4], vv[2][4];
  mbar_wait(sb + OFF_BAR + 8 * (B_KV + slab), 0);
#pragma unroll
  for (int h = 0; h < 2; h++) {
#pragma unroll
    for (int j = 0; j < 4; j++) {
      const uint32_t a = base + 128 * j;
      ldsm4t(kk[h][j], a + (((w + 4 * h) ^ ((a >> 7) & 7)) << 4));
    }
    const uint32_t a = base + KVS_V;
    ldsm4t(vv[h], a + (((w + 4 * h) ^ ((a >> 7) & 7)) << 4));
  }
#pragma unroll
  for (int h = 0; h < 2; h++) {
    uint32_t (&k)[4][4] = kk[h];
    uint32_t (&v)[4] = vv[h];
    const uint32_t w0 = __byte_perm(sw[h].x, 0, 0x1010), w1 = __byte_perm(sw[h].x, 0, 0x3232);
    const uint32_t w2 = __byte_perm(sw[h].y, 0, 0x1010), w3 = __byte_perm(sw[h].y, 0, 0x3232);
#pragma unroll
    for (int m = 0; m < 4; m++)
      v[m] = bmul(badd(badd(badd(bmul(k[0][m], w3), bmul(k[1][m], w2)), bmul(k[2][m], w1)), bmul(k[3][m], w0)), v[m]);
    uint32_t a[4];
#pragma unroll
    for (int m = 0; m < 4; m++) a[m] = (t & 1) ? v[(m + 3) & 3] : v[m];
    res[h] = (t & 2) ? make_uint4(a[2], a[3], a[0], a[1]) : make_uint4(a[0], a[1], a[2], a[3]);
  }
}

template <int N> __device__ __forceinline__ void prep_gate(const Params& p, int row, int lane) {
  uint2 gw[5], x[4 * N][5];
#pragma unroll
  for (int j = 0; j < 5; j++) gw[j] = ldg64(reinterpret_cast<const uint2*>(p.gate_w) + lane + 32 * j);
#pragma unroll
  for (int i = 0; i < 4 * N; i++)
#pragma unroll
    for (int j = 0; j < 5; j++) x[i][j] = ldg64(reinterpret_cast<const uint2*>(p.q) + (row + i) * (DIM / 4) + lane + 32 * j);
#pragma unroll
  for (int n = 0; n < N; n++) {
    float s[4];
#pragma unroll
    for (int i = 0; i < 4; i++) {
      s[i] = 0.f;
#pragma unroll
      for (int j = 0; j < 5; j++) {
        const uint32_t m0 = bmul(x[4 * n + i][j].x, gw[j].x), m1 = bmul(x[4 * n + i][j].y, gw[j].y);
        s[i] += (bf_lo(m0) + bf_hi(m0)) + (bf_lo(m1) + bf_hi(m1));
      }
    }
    const bool h = lane & 16, q = lane & 8;
    const float a = (h ? s[2] : s[0]) + __shfl_xor_sync(0xffffffffu, h ? s[0] : s[2], 16);
    const float c = (h ? s[3] : s[1]) + __shfl_xor_sync(0xffffffffu, h ? s[1] : s[3], 16);
    float z = (q ? c : a) + __shfl_xor_sync(0xffffffffu, q ? a : c, 8);
#pragma unroll
    for (int o = 4; o > 0; o >>= 1) z += __shfl_xor_sync(0xffffffffu, z, o);
    z = bf_lo(pack2(z, 0.f));
    if ((lane & 7) == 0) g_gate[row + 4 * n + (lane >> 3)] = bf_lo(pack2(__fdividef(1.f, 1.f + __expf(-z)), 0.f));
  }
}

__device__ __forceinline__ uint32_t bmax(uint32_t a, uint32_t b) {
  uint32_t d;
  asm("max.bf16x2 %0, %1, %2;" : "=r"(d) : "r"(a), "r"(b));
  return d;
}
__device__ __forceinline__ void softmax_two(const float (&l)[2][2], uint32_t& p0, uint32_t& p1) {
  constexpr float kScale = 0.22360679774997896f, kLog2e = 1.4426950408889634f;
  const uint32_t r0 = pack2(l[0][0], l[1][0]), r1 = pack2(l[0][1], l[1][1]);
  const uint32_t x0 = pack2(bf_lo(r0) * kScale, bf_hi(r0) * kScale), x1 = pack2(bf_lo(r1) * kScale, bf_hi(r1) * kScale);
  uint32_t m = bmax(x0, x1);
  m = bmax(m, __shfl_xor_sync(0xffffffffu, m, 1));
  m = bmax(m, __shfl_xor_sync(0xffffffffu, m, 2));
  const float m0 = bf_lo(m) * kLog2e, m1 = bf_hi(m) * kLog2e;
  p0 = pack2(ex2(bf_lo(x0) * kLog2e - m0), ex2(bf_lo(x1) * kLog2e - m0));
  p1 = pack2(ex2(bf_hi(x0) * kLog2e - m1), ex2(bf_hi(x1) * kLog2e - m1));
}

__device__ __forceinline__ void halo_read(uint32_t (&kpv)[10], uint32_t (&vpv)[10], uint32_t (&tg)[7], const uint4* hp) {
#pragma unroll
  for (int j = 0; j < 7; j++) {
    uint32_t x0, x1, x2;
    asm volatile("ld.relaxed.gpu.global.v4.u32 {%0, %1, %2, %3}, [%4];"
                 : "=r"(x0), "=r"(x1), "=r"(x2), "=r"(tg[j]) : "l"(hp + 32 * j) : "memory");
    if (j < 4) kpv[3 * j] = x0; else vpv[3 * j - 10] = x0;
    if (j < 3) kpv[3 * j + 1] = x1; else vpv[3 * j - 9] = x1;
    if (j < 3) kpv[3 * j + 2] = x2; else if (j < 6) vpv[3 * j - 8] = x2;
  }
}

template <int ROT>
__device__ __forceinline__ void pack_qkv(const float* acc, uint32_t (&qlo)[10], uint32_t (&qhi)[10], uint32_t (&klo)[10],
                                         uint32_t (&khi)[10], uint32_t (&vlo)[10], uint32_t (&vhi)[10]) {
#pragma unroll
  for (int j = 0; j < 10; j++) {
    const int x = (j + ROT) % 10, tq = x < 8 ? x : 16 + x, tk = x < 8 ? 8 + x : 18 + x, tv = x < 8 ? 16 + x : 20 + x;
    khi[j] = pack2(acc[4 * tk + 2], acc[4 * tk + 3]);
    vhi[j] = movm(pack2(acc[4 * tv + 2], acc[4 * tv + 3]));
    qlo[j] = pack2(acc[4 * tq], acc[4 * tq + 1]);
    qhi[j] = pack2(acc[4 * tq + 2], acc[4 * tq + 3]);
    klo[j] = pack2(acc[4 * tk], acc[4 * tk + 1]);
    vlo[j] = pack2(acc[4 * tv], acc[4 * tv + 1]);
    asm volatile("" : "+r"(khi[j]), "+r"(qlo[j]), "+r"(qhi[j]), "+r"(klo[j]), "+r"(vlo[j]));
  }
}

template <int ROT> __device__ __forceinline__ void halo_send(const float* acc, uint4* ho, uint32_t tag) {
#pragma unroll
  for (int j = 0; j < 7; j++) {
    uint32_t x[3];
#pragma unroll
    for (int e = 0; e < 3; e++) {
      const int i = 3 * j + e, y = (i % 10 + ROT) % 10, tk = y < 8 ? 8 + y : 18 + y, tv = y < 8 ? 16 + y : 20 + y;
      x[e] = i < 10 ? pack2(acc[4 * tk + 2], acc[4 * tk + 3]) : i < 20 ? movm(pack2(acc[4 * tv + 2], acc[4 * tv + 3])) : 0u;
    }
    asm volatile("st.relaxed.gpu.global.v4.u32 [%0], {%1, %2, %3, %4};" ::"l"(ho + 32 * j), "r"(x[0]), "r"(x[1]), "r"(x[2]), "r"(tag) : "memory");
  }
}

__device__ __forceinline__ void attention(float* acc, uint32_t sb, int b, int par, int w, int lane, uint32_t tag) {
  const int g = lane >> 2, t = lane & 3;
  uint32_t klo[10], khi[10], vlo[10], vhi[10], qlo[10], qhi[10], kpv[10], vpv[10];
  if (HALO_FIRST && w == 3 && b < NCTA - 8) {
    uint4* ho = g_halo + (b * 2 + par) * 224 + lane;
    if (tail_first(b & 7)) halo_send<8>(acc, ho, tag);
    else halo_send<0>(acc, ho, tag);
    TSIF(par == 0, 76);
    pin<120>(acc);
  }
  if (tail_first(b & 7)) pack_qkv<8>(acc, qlo, qhi, klo, khi, vlo, vhi);
  else pack_qkv<0>(acc, qlo, qhi, klo, khi, vlo, vhi);
  const uint32_t xa = sb + OFF_KVX + (par * 3) * 2560 + lane * 16;
  if (w < 3) {
    sts128(xa + w * 2560, khi[0], khi[1], khi[2], khi[3]);
    sts128(xa + w * 2560 + 512, khi[4], khi[5], khi[6], khi[7]);
    sts128(xa + w * 2560 + 1024, khi[8], khi[9], vhi[0], vhi[1]);
    sts128(xa + w * 2560 + 1536, vhi[2], vhi[3], vhi[4], vhi[5]);
    sts128(xa + w * 2560 + 2048, vhi[6], vhi[7], vhi[8], vhi[9]);
  } else if (!HALO_FIRST && b < NCTA - 8) {
    uint4* ho = g_halo + (b * 2 + par) * 224 + lane;
#pragma unroll
    for (int j = 0; j < 7; j++) {
      const uint32_t x0 = j < 4 ? khi[3 * j] : vhi[3 * j - 10], x1 = j < 3 ? khi[3 * j + 1] : vhi[3 * j - 9];
      const uint32_t x2 = j < 3 ? khi[3 * j + 2] : j < 6 ? vhi[3 * j - 8] : 0u;
      asm volatile("st.relaxed.gpu.global.v4.u32 [%0], {%1, %2, %3, %4};" ::"l"(ho + 32 * j), "r"(x0), "r"(x1), "r"(x2), "r"(tag) : "memory");
    }
  }
  TSIF(par == 0 && w == 1, 64);
  TSIF(par == 0 && w == 3 && !HALO_FIRST, 76);
#pragma unroll
  for (int j = 0; j < 10; j++) vlo[j] = movm(vlo[j]);
  const bool far0 = 2 * t > g, far1 = 2 * t + 1 > g;
  const uint32_t mfar = (far0 ? 0x0000FFFFu : 0u) | (far1 ? 0xFFFF0000u : 0u);
  float slo[4][2], shi[4][2], lg[2][2];
  uint32_t phi[4], plo[4], qml[4], qmh[4];
#pragma unroll
  for (int h = 0; h < 4; h++) {
    const int f = h == 0 ? 0 : h == 1 ? 3 : h == 2 ? 5 : 8, hf = h < 2 ? 2 : 7;
    const bool mine = (h & 1) ? t >= 2 : t < 2;
    qml[h] = mine ? qlo[hf] : 0u;
    qmh[h] = mine ? qhi[hf] : 0u;
    float a[4] = {0.f, 0.f, 0.f, 0.f}, c[4] = {0.f, 0.f, 0.f, 0.f};
    mma16816(a, qlo[f], qhi[f], qlo[f + 1], qhi[f + 1], klo[f], klo[f + 1]);
    mma16816(c, qlo[f], qhi[f], qlo[f + 1], qhi[f + 1], khi[f], khi[f + 1]);
    mma1688(a, qml[h], qmh[h], klo[hf]);
    mma1688(c, qml[h], qmh[h], khi[hf]);
    slo[h][0] = a[0];
    slo[h][1] = a[1];
    shi[h][0] = lg[h & 1][0] = far0 ? a[2] : c[2];
    shi[h][1] = lg[h & 1][1] = far1 ? a[3] : c[3];
    if (!ATT_MERGE && (h & 1)) softmax_two(lg, phi[h - 1], phi[h]);
  }
  TSIF(par == 0 && w == 1, 65);
  wg_sync(1 + par);
  TSIF(par == 0 && w == 1, 66);
  const bool nohist = (w == 0) && (b < 8);
  const uint4* hp = g_halo + ((b - 8) * 2 + par) * 224 + lane;
  uint32_t tg[7];
  if (w > 0) {
    const uint4 v0 = lds128(xa + (w - 1) * 2560), v1 = lds128(xa + (w - 1) * 2560 + 512), v2 = lds128(xa + (w - 1) * 2560 + 1024);
    const uint4 v3 = lds128(xa + (w - 1) * 2560 + 1536), v4 = lds128(xa + (w - 1) * 2560 + 2048);
    kpv[0] = v0.x; kpv[1] = v0.y; kpv[2] = v0.z; kpv[3] = v0.w; kpv[4] = v1.x; kpv[5] = v1.y; kpv[6] = v1.z; kpv[7] = v1.w;
    kpv[8] = v2.x; kpv[9] = v2.y; vpv[0] = v2.z; vpv[1] = v2.w; vpv[2] = v3.x; vpv[3] = v3.y; vpv[4] = v3.z; vpv[5] = v3.w;
    vpv[6] = v4.x; vpv[7] = v4.y; vpv[8] = v4.z; vpv[9] = v4.w;
  } else if (nohist) {
#pragma unroll
    for (int j = 0; j < 10; j++) kpv[j] = vpv[j] = 0u;
  } else {
    TSIF(par == 0, 77);
    halo_read(kpv, vpv, tg, hp);
  }
  if (w == 0 && !nohist) {
    int spins = 0;
    while (true) {
      bool ok = true;
#pragma unroll
      for (int j = 0; j < 7; j++) ok = ok && tg[j] == tag;
      if (__all_sync(0xffffffffu, ok) || ++spins > SPIN_LIMIT) break;
      halo_read(kpv, vpv, tg, hp);
    }
    TSIF(par == 0, 79);
  }
#pragma unroll
  for (int h = 0; h < 4; h++) {
    const int f = h == 0 ? 0 : h == 1 ? 3 : h == 2 ? 5 : 8, hf = h < 2 ? 2 : 7;
    float a[4] = {0.f, 0.f, 0.f, 0.f};
    mma16816(a, qlo[f], qhi[f], qlo[f + 1], qhi[f + 1], kpv[f], kpv[f + 1]);
    mma1688(a, qml[h], qmh[h], kpv[hf]);
    const float ninf = __int_as_float(0xff800000);
    lg[h & 1][0] = far0 ? (nohist ? ninf : a[0]) : slo[h][0];
    lg[h & 1][1] = far1 ? (nohist ? ninf : a[1]) : slo[h][1];
    if (h & 1) {
      softmax_two(lg, plo[h - 1], plo[h]);
      if (ATT_MERGE) {
        const float lh[2][2] = {{shi[h - 1][0], shi[h - 1][1]}, {shi[h][0], shi[h][1]}};
        softmax_two(lh, phi[h - 1], phi[h]);
      }
    }
  }
  TSIF(par == 0 && w <= 1, 67 + w);
  uint32_t ov[20];
#pragma unroll
  for (int hp = 0; hp < 2; hp++) {
    const int hf = hp ? 7 : 2;
    float sh[4] = {0.f, 0.f, 0.f, 0.f}, i0 = 0.f, i1 = 0.f;
#pragma unroll
    for (int e = 0; e < 2; e++) {
      const int h = 2 * hp + e, f = h == 0 ? 0 : h == 1 ? 3 : h == 2 ? 5 : 8;
      const uint32_t a0 = plo[h] & mfar, a2 = plo[h] & ~mfar, a3 = phi[h] & mfar, c1 = phi[h] & ~mfar;
      float sum[4] = {0.f, 0.f, 0.f, 0.f};
      mma1688(sum, plo[h], phi[h], 0x3F803F80u);
      const float r0 = rcp(sum[0]), r1 = rcp(sum[2]);
#pragma unroll
      for (int j = f; j < f + 2; j++) {
        float o[4] = {0.f, 0.f, 0.f, 0.f};
        mma16816(o, a0, 0u, a2, a3, vpv[j], vlo[j]);
        mma1688(o, 0u, c1, vhi[j]);
        ov[2 * j] = pack2(o[0] * r0, o[1] * r0);
        ov[2 * j + 1] = pack2(o[2] * r1, o[3] * r1);
      }
      const bool mine = e ? g >= 4 : g < 4;
      mma16816(sh, a0, 0u, a2, a3, mine ? vpv[hf] : 0u, mine ? vlo[hf] : 0u);
      mma1688(sh, 0u, c1, mine ? vhi[hf] : 0u);
      if (e == 0 || t >= 2) {
        i0 = r0;
        i1 = r1;
      }
    }
    ov[2 * hf] = pack2(sh[0] * i0, sh[1] * i0);
    ov[2 * hf + 1] = pack2(sh[2] * i1, sh[3] * i1);
  }
  TS(32 + 4 * par + w);
  mbar_wait(sb + OFF_BAR + 8 * B_P1, 0);
  const uint32_t oa = sb + OFF_OA + (lane >> 4) * 2048 + (32 * w + 2 * (lane & 15) + par) * 16;
#pragma unroll
  for (int j = 0; j < 5; j++) stsm4(oa + 4096 * j, ov + 4 * j);
  TSIF(par == 0 && w == 0, 120);
  fence_async_smem();
  TSIF(par == 0 && w == 0, 121);
  __syncwarp();
  if (lane == 0) mbar_arrive(sb + OFF_BAR + 8 * B_ATTN);
  TSM(w == 0 || w == 2, 122 + par + (w == 2 ? 3 : 0));
}

struct Maps {
  CUtensorMap x, wm, wt, k, v, y, wo, qm, qt, om, ot, u;
};

__device__ __forceinline__ void load_stage(uint32_t sb, int kb, int b, const Maps& m) {
  const uint32_t st = sb + (kb & 3) * STAGE_BYTES, bar = sb + OFF_BAR + 8 * (B_FULL1 + (kb & 3));
  const int r = b >> 3, hg = b & 7, slab = kb - KV_KB;
  const bool kv = slab >= 0 && slab < 5;
  const uint32_t kbar = sb + OFF_BAR + 8 * (B_KV + slab), dst = sb + OFF_KVS + slab * KVS_BYTES;
  mbar_expect_tx(bar, STAGE_BYTES);
  if (kv) mbar_expect_tx(kbar, KVS_BYTES);
  tma_3d(st, &m.x, 64 * kb, 64 * r, 0, bar);
  if (kv && KV_MIX) tma_3d(dst, &m.k, 0, 32 * (b >> 1) - 3, 2 * slab + (b & 1), kbar);
  tma_3d(st + ST_W, &m.wm, 80 * hg + (tail_first(hg) ? 16 : 0), 64 * kb, 0, bar);
  if (kv && KV_MIX) tma_3d(dst + KVS_V, &m.v, 0, 32 * (b >> 1), 2 * slab + (b & 1), kbar);
  tma_3d(st + ST_WT, &m.wt, 80 * hg + (tail_first(hg) ? 0 : 64), 64 * kb, 0, bar);
  if (kv && !KV_MIX) tma_3d(dst, &m.k, 0, 32 * (b >> 1) - 3, 2 * slab + (b & 1), kbar);
  if (kv && !KV_MIX) tma_3d(dst + KVS_V, &m.v, 0, 32 * (b >> 1), 2 * slab + (b & 1), kbar);
}

__global__ void __launch_bounds__(NTHR, 1) fused_kernel(const __grid_constant__ Maps m, const Params p) {
  extern __shared__ __align__(1024) uint8_t smem[];
  const uint32_t sb = (uint32_t)__cvta_generic_to_shared(smem);
  const uint32_t bars = sb + OFF_BAR;
  const int tid = threadIdx.x, lane = tid & 31;
  int b = blockIdx.x;
  if (BMAP == 1) b = (((b & 63) >> 3) * 2 + (b & 1)) * 8 + (((b < 64 ? 0x6521 : 0x7430) >> (4 * ((b >> 1) & 3))) & 7);
  if (BMAP == 2) b = ((b & 63) >> 2) * 8 + (((b < 64 ? 0x6521 : 0x7430) >> (4 * (b & 3))) & 7);
  if (BMAP == 3) b = (((b & 63) >> 3) * 2 + (b & 1)) * 8 + (((b < 64 ? 0x7430 : 0x6521) >> (4 * ((b >> 1) & 3))) & 7);
  if (BMAP == 4) b = (((b >> 4) * 2 + (b & 1)) * 8) + ((b >> 1) & 7);
  if (BMAP == 5) b = 127 - b;
  const int r = b >> 3, hg = b & 7;

  if (tid == T_ISSUE) {
    TSM(true, 0);
#pragma unroll
    for (int i = 0; i < 4; i++) mbar_init(bars + 8 * (B_FULL1 + i), 1);
#pragma unroll
    for (int i = 0; i < 3; i++) mbar_init(bars + 8 * (B_KV + i), 1);
    fence_async_smem();
#pragma unroll 1
    for (int kb = 0; kb <= PRE2; kb++) load_stage(sb, kb, b, m);
  } else if (tid >= T_PF && tid < T_PF + 12) {
    tm_prefetch(&m.x + (tid - T_PF));
  } else if (tid == T_INIT) {
#pragma unroll
    for (int i = 0; i < 4; i++) mbar_init(bars + 8 * (B_EMPTY1 + i), 8);
#pragma unroll
    for (int i = 0; i < 8; i++) mbar_init(bars + 8 * (B_FULL2 + i), 1);
#pragma unroll
    for (int i = 0; i < 4; i++) mbar_init(bars + 8 * (B_EMPTY2 + i), 8);
#pragma unroll
    for (int i = 0; i < 4; i++) mbar_init(bars + 8 * (B_U + i), 1);
    mbar_init(bars + 8 * B_HA, 4);
    mbar_init(bars + 8 * B_GATE, 4);
    mbar_init(bars + 8 * B_HB, 1);
    mbar_init(bars + 8 * B_KVD, 4);
    mbar_init(bars + 8 * B_QF, 1);
    mbar_init(bars + 8 * B_ATTN, 8);
    mbar_init(bars + 8 * B_P1, 8);
    mbar_init(bars + 8 * B_C34, 1);
#pragma unroll
    for (int i = 0; i < 5; i++) mbar_init(bars + 8 * (B_YST + i), 4);
#pragma unroll
    for (int i = 0; i < 5; i++) mbar_init(bars + 8 * (B_US + i), 4);
    mbar_init(bars + 8 * B_YSIG, 1);
    mbar_init(bars + 8 * B_YFULL, 1);
    mbar_init(bars + 8 * B_EPOCH, 1);
    mbar_init(bars + 8 * B_PREP, 4);
    mbar_init(bars + 8 * B_USIG, 1);
    mbar_init(bars + 8 * B_WST, 1);
#pragma unroll
    for (int i = 3; i < 5; i++) mbar_init(bars + 8 * (B_KV + i), 1);
    mbar_init(bars + 8 * B_E3, 8);
    mbar_init(bars + 8 * B_LAST, 1);
    mbar_init(bars + 8 * B_OSIG, 1);
    mbar_init(bars + 8 * B_WOP, 1);
    fence_async_smem();
  }
  const int warp = __shfl_sync(0xffffffffu, tid >> 5, 0), wg = warp >> 2, w = warp & 3;
  __syncthreads();

  if (wg == 3) {
    asm volatile("setmaxnreg.dec.sync.aligned.u32 56;");
    if (w == 0) {
      if (lane == 0) {
#pragma unroll 1
        for (int kb = 1 + PRE2; kb < 10; kb++) {
          if (kb >= 4) mbar_wait(bars + 8 * (kb == 7 ? B_E3 : B_EMPTY1 + (kb & 3)), (kb >> 3) & 1);
          TSIF(kb >= 4, 44 + kb);
          load_stage(sb, kb, b, m);
          TSIF(kb == 3, 60);
          if (kb == TRIG_KB) mbar_arrive(bars + 8 * B_LAST);
        }
        mbar_wait(bars + 8 * B_WOP, 0);
        mbar_wait(bars + 8 * WL_TRIG, 0);
        mbar_wait(bars + 8 * B_EPOCH, 0);
        flag_wait(g_cnt + C_W + 32 * hg, (lds32(sb + OFF_EPOCH) + 1) * 16);
        TS(30);
#pragma unroll 1
        for (int j = 0; j < 8; j++) {
          if (j >= 6) mbar_wait(bars + 8 * (B_EMPTY2 + j - 6), 0);
          if (j == 4) mbar_wait(bars + 8 * B_ATTN, 0);
          TSIF(j >= 6, 100 + j);
          if (RF_GATE && j == 6) mbar_wait(bars + 8 * B_YSIG, 0);
          mbar_expect_tx(bars + 8 * (B_FULL2 + j), j == 0 ? WO_BYTES : j == 5 ? O_BYTES + WO_BYTES + 512 : O_BYTES + WO_BYTES);
          bulk_load(sb + off_w(j), g_WO + (hg * 8 + step_src(hg, j)) * 800, WO_BYTES, bars + 8 * (B_FULL2 + j));
        }
        mbar_wait(bars + 8 * (B_EMPTY2 + 3), 0);
        mbar_expect_tx(bars + 8 * B_QF, O_BYTES);
        tma_2d(sb + OFF_QS, &m.qm, 80 * hg, 128 * r, bars + 8 * B_QF);
        tma_2d(sb + OFF_QT, &m.qt, 80 * hg + 64, 128 * r, bars + 8 * B_QF);
      }
    } else if (w == 1) {
      unsigned epoch = 0;
      if (lane == 0) {
        epoch = atomicAdd(g_cnt + C_LAUNCH, 1u) / NCTA;
        asm volatile("st.shared.u32 [%0], %1;" ::"r"(sb + OFF_EPOCH), "r"(epoch) : "memory");
        mbar_arrive(bars + 8 * B_EPOCH);
        mbar_wait(bars + 8 * B_KVD, 0);
        mbar_expect_tx(bars + 8 * B_HB, 5 * 4096);
#pragma unroll 1
        for (int c = 0; c < 5; c++) {
          if (c == 3) mbar_wait(bars + 8 * B_S3, 0);
          bulk_load(sb + off_ch(c) + U_BYTES, p.ssm_k + (5 * b + c) * SEQ, 4096, bars + 8 * B_HB);
        }
#pragma unroll
        for (int c = 0; c < 4; c++) mbar_expect_tx(bars + 8 * (B_U + c), c < 3 ? U_BYTES : 2 * U_BYTES);
        const uint4* usrc = g_U + 5 * b * U_PITCH;
        mbar_wait(bars + 8 * B_USIG, 0);
        flag_wait(g_cnt + C_PREP + 32 * (b & 15), (epoch + 1) * NCTA);
        TS(23);
#pragma unroll
        for (int c = 0; c < 5; c++) {
          if (c == 3) mbar_wait(bars + 8 * (B_U + 2), 0);
          bulk_load(sb + off_ch(c), usrc + c * U_PITCH, U_BYTES, bars + 8 * (B_U + (c < 3 ? c : 3)));
          TSIF(c == 0 || c == 4, 116 + (c >> 2));
        }
      }
      epoch = __shfl_sync(0xffffffffu, epoch, 0);
      if (lane < 8) {
        const int src = (b & ~7) | step_src(hg, lane);
        mbar_wait(bars + 8 * OP_TRIG, 0);
        TS(20);
        bool seen = false;
#pragma unroll 1
        for (int spins = 0; spins < SPIN_LIMIT; spins++) {
          const bool now = !seen && (int)(flag_read(g_cnt + C_O + 32 * src) - (epoch + 1)) >= 0;
          if (now && lane >= 1 && lane < 4) bulk_load(sb + off_o(lane), g_O + src * 1280, O_BYTES, bars + 8 * (B_FULL2 + lane));
          seen = seen || now;
          if (__all_sync(0xff, seen)) break;
        }
        TS(21);
        if (lane == 5) bulk_load(sb + OFF_GATE, g_gate + 128 * r, 512, bars + 8 * (B_FULL2 + 5));
#pragma unroll 1
        for (int j = 4; j < 8; j++) {
          if (lane == j) {
            mbar_wait(bars + 8 * (j < 6 ? B_C34 : B_EMPTY2 + j - 6), 0);
            if (RF_GATE && j == 6) mbar_wait(bars + 8 * B_YSIG, 0);
            bulk_load(sb + off_o(j), g_O + src * 1280, O_BYTES, bars + 8 * (B_FULL2 + j));
          }
          __syncwarp(0xff);
        }
        TS(22);
      }
    } else if (w == 2) {
      mbar_wait(bars + 8 * B_PREP, 0);
      flag_signal(g_cnt + C_PREP, 16, lane);
      TS(25);
      if (lane == 0) mbar_arrive(bars + 8 * B_USIG);
      mbar_wait(bars + 8 * B_GATE, 0);
      if (((NOMB & 1) || O_RB) && lane == 0) asm volatile("fence.release.gpu;" ::: "memory");
      mbar_wait(bars + 8 * B_ATTN, 0);
      if (lane == 0) {
        if (O_DEFER) mbar_wait(bars + 8 * (B_U + 3), 0);
        asm volatile("cp.async.bulk.global.shared::cta.bulk_group [%0], [%1], 20480;\ncp.async.bulk.commit_group;"
                     ::"l"(g_O + b * 1280), "r"(sb + OFF_OA) : "memory");
        if (O_RB) asm volatile("cp.async.bulk.wait_group.read 0;" ::: "memory");
        else asm volatile("cp.async.bulk.wait_group 0;\nfence.proxy.async.global;" ::: "memory");
      }
      TS(74);
      if (O_RB) {
        __syncwarp();
        unsigned v[5];
#pragma unroll
        for (int c = 0; c < 5; c++) v[c] = flag_read(reinterpret_cast<const unsigned*>(g_O + b * 1280 + 256 * c + 8 * lane + 7));
        const unsigned dep = __reduce_or_sync(0xffffffffu, (v[0] ^ v[1] ^ v[2] ^ v[3] ^ v[4]) & p.zero);
        if (lane == 0) flag_bump(g_cnt + C_O + 32 * b + dep);
      } else if (!(NOMB & 1)) flag_signal(g_cnt + C_O + 32 * b, 1, lane);
      else if (lane == 0) flag_bump(g_cnt + C_O + 32 * b);
      TS(26);
      if (lane == 0) mbar_arrive(bars + 8 * B_OSIG);

    } else {
      if (lane == 0) {
        const int np = !(BAL & 2) ? 1 : blockIdx.x >= 64 ? 2 : 0;
        mbar_wait(bars + 8 * B_P1, 0);
        mbar_wait(bars + 8 * WB_TRIG, 0);
        mbar_expect_tx(bars + 8 * B_WST, np * (WO_BYTES / 2));
#pragma unroll 1
        for (int i = 0; i < np; i++) tma_3d(sb + OFF_WS + 6400 * i, &m.wo, 0, 40 * r, 5 * (hg ^ i), bars + 8 * B_WST);
        mbar_wait(bars + 8 * B_WST, 0);
        mbar_wait(bars + 8 * WO_TRIG, 0);
#pragma unroll 1
        for (int n = 0; n < 5 * np; n++)
          asm volatile("cp.async.bulk.global.shared::cta.bulk_group [%0], [%1], 1280;"
                       ::"l"(g_WO + ((hg ^ (n >= 5)) * 8 + (r >> 1)) * 800 + (r & 1) * 80 + 160 * (n >= 5 ? n - 5 : n)), "r"(sb + OFF_WS + 1280 * n) : "memory");
        if (np) {
          asm volatile("cp.async.bulk.commit_group;\ncp.async.bulk.wait_group 0;\nfence.proxy.async.global;" ::: "memory");
          if (!(NOMB & 4)) asm volatile("fence.release.gpu;" ::: "memory");
        }
#pragma unroll 1
        for (int i = 0; i < np; i++) flag_bump(g_cnt + C_W + 32 * (hg ^ i));
        mbar_arrive(bars + 8 * B_WOP);
        TS(71);
#pragma unroll 1
        for (int c = 0; c < 5; c++) {
          mbar_wait(bars + 8 * (B_YST + c), 0);
          asm volatile("cp.async.bulk.global.shared::cta.bulk_group [%0], [%1], 4096;\ncp.async.bulk.commit_group;"
                       ::"l"(g_Y + (5 * b + c) * Y_PITCH), "r"(sb + off_ch(c)) : "memory");
          if (c == 2) {
            asm volatile("cp.async.bulk.wait_group.read 0;" ::: "memory");
            mbar_arrive(bars + 8 * B_C34);
          }
        }
        if (Y_RB) asm volatile("cp.async.bulk.wait_group.read 0;" ::: "memory");
        else asm volatile("cp.async.bulk.wait_group 0;\nfence.proxy.async.global;" ::: "memory");
        TS(75);
      }
      unsigned dep = 0;
      if (Y_RB) {
        __syncwarp();
        unsigned v[5];
#pragma unroll
        for (int c = 0; c < 5; c++) v[c] = flag_read(reinterpret_cast<const unsigned*>(g_Y + (5 * b + c) * Y_PITCH + 8 * lane + 7));
        dep = __reduce_or_sync(0xffffffffu, (v[0] ^ v[1] ^ v[2] ^ v[3] ^ v[4]) & p.zero);
      }
      if (lane == 0) {
        if (!Y_RB && !(NOMB & 2)) asm volatile("fence.release.gpu;" ::: "memory");
        flag_bump(g_cnt + C_Y + 32 * (b >> 4) + dep);
        TS(27);
        mbar_arrive(bars + 8 * B_YSIG);
        mbar_expect_tx(bars + 8 * B_YFULL, 20480);
        flag_wait(g_cnt + C_Y + 32 * hg, (lds32(sb + OFF_EPOCH) + 1) * 16);
        TS(24);
        tma_2d(sb + OFF_YT, &m.y, 128 * r, 80 * hg, bars + 8 * B_YFULL);
        tma_2d(sb + OFF_YT + 10240, &m.y, 128 * r + 64, 80 * hg, bars + 8 * B_YFULL);
      }
    }
  } else {
    asm volatile("setmaxnreg.inc.sync.aligned.u32 152;");
    if (wg < 2) {
      float acc[120];
#pragma unroll
      for (int i = 0; i < 120; i++) acc[i] = 0.f;
      const uint32_t da = desc_lo(sb + wg * 8192, 16), db = desc_lo(sb + ST_W, 8192), dc = desc_lo(sb + ST_WT, 2048);
      if (PW1) pin<120>(acc);
      if (PW1 == 2) mbar_wait(bars + 8 * B_FULL1, 0);
#pragma unroll 1
      for (int kb = 0; kb < 10; kb++) {
        mbar_wait(bars + 8 * (B_FULL1 + (kb & 3)), (kb >> 2) & 1);
        const uint32_t so = (kb & 3) * (STAGE_BYTES >> 4);
        wg_fence();
#pragma unroll
        for (int k = 0; k < 4; k++) {
          WgSST<192>::mma<HI_SW128, HI_SW128>(acc, da + so + 2 * k, db + so + 128 * k, 1);
          WgSST<48>::mma<HI_SW128, HI_SW32>(acc + 96, da + so + 2 * k, dc + so + 32 * k, 1);
        }
        wg_commit();
        wg_wait<1>();
        if (kb > 0 && lane == 0) mbar_arrive(bars + 8 * (kb == 4 ? B_E3 : B_EMPTY1 + ((kb - 1) & 3)));
      }
      mbar_wait(bars + 8 * B_EPOCH, 0);
      const uint32_t tag = lds32(sb + OFF_EPOCH) + 1;
      mbar_wait(bars + 8 * B_S3, 0);
      wg_wait<0>();
      pin<120>(acc);
      if (lane == 0) mbar_arrive(bars + 8 * B_P1);
      TSM(w == 0, 3 + wg);
      attention(acc, sb, b, wg, w, lane, tag);
    } else {
      const int tw = tid & 127, chl = 64 * (b & 1) + 8 * w + (lane >> 2);
      uint4* up = g_U + chl * U_PITCH + ((4 * (b >> 1) + (lane & 3)) ^ ((b >> 2) & 1));
      uint2 sw[10];
      uint32_t dv = 0;
      if (lane < 5) dv = __ldg(reinterpret_cast<const unsigned short*>(p.ssm_D) + 5 * b + lane);
#pragma unroll
      for (int i = 0; i < 10; i++) sw[i] = ldg64(reinterpret_cast<const uint2*>(p.shift_k) + chl + 128 * (i >> 1) + 32 * (i & 1));
      uint32_t tab[12];
      uint32_t tt[2];
      fft_tables(tab, tw);
      fft_twiddles(tt, tw);
      uint4 res[10];
#pragma unroll
      for (int i = 0; i < 10; i++) res[i] = make_uint4(0, 0, 0, 0);
#pragma unroll 1
      for (int slab = 0; slab < 5; slab++) {
#pragma unroll
        for (int i = 0; i < 8; i++) res[i] = res[i + 2];
        prep_slab(res + 8, sw, sb, slab, w, lane);
        TSIF(w == 0, 99 + 4 * slab);
#pragma unroll
        for (int i = 0; i < 8; i++) sw[i] = sw[i + 2];
      }
      TSIF(w == 0, 28);
      __syncwarp();
      if (lane == 0) mbar_arrive(bars + 8 * B_KVD + ((res[8].x ^ res[9].x) & p.zero));
      mbar_wait(bars + 8 * B_KVD, 0);
      fft_tables_store(tab, sb, tw);
      mbar_wait(bars + 8 * B_LAST, 0);
#pragma unroll
      for (int i = 0; i < 10; i++) up[(128 * (i >> 1) + 32 * (i & 1)) * U_PITCH] = res[i];
      __syncwarp();
      if (lane == 0) mbar_arrive(bars + 8 * B_PREP);
      TSIF(w == 0 && !U_TMA, 5);
      mbar_wait(bars + 8 * (G_AFTER ? B_USIG : B_LAST), 0);
      if (!(BAL & 1)) prep_gate<1>(p, 16 * b + 4 * w, lane);
      else if (blockIdx.x >= 64) prep_gate<2>(p, 16 * (b & ~1) + 8 * w, lane);
      __syncwarp();
      if (lane == 0) mbar_arrive(bars + 8 * B_GATE);
      TSIF(w == 0, 72);
      mbar_wait(bars + 8 * B_HB, 0);
      TSIF(w == 0, 2);
      const uint32_t ha = sb + U_BYTES + ((tw >> 3) * 16 + 8 + (tw & 7)) * 16;
      uint4 hv[5];
#pragma unroll
      for (int c = 0; c < 5; c++) hv[c] = lds128(ha + off_ch(c));
      __syncwarp();
#pragma unroll
      for (int c = 0; c < 5; c++) sts128((ha ^ 16) + off_ch(c), hv[c].x, hv[c].y, hv[c].z, hv[c].w);
      asm volatile("st.shared.v2.u32 [%0], {%1, %2};" ::"r"(sb + OFF_TT + 8 * tw), "r"(tt[0]), "r"(tt[1]) : "memory");
      if (tw < 5) asm volatile("st.shared.f32 [%0], %1;" ::"r"(sb + OFF_D + 4 * tw), "f"(bf_lo(dv) * 0.125f) : "memory");
      fence_async_smem();
      __syncwarp();
      if (lane == 0) mbar_arrive(bars + 8 * B_HA);
      TSIF(w == 0, 6);
    }

    FftConst fc;
    TSM(w == 0 && wg == 0, 104);
    mbar_wait(bars + 8 * B_HA, 0);
    fft_matrices(fc, sb, w, lane);
    TSM(w == 0 && wg == 0, 105);
    if (ATT_GATE && !H_EARLY) mbar_wait(bars + 8 * B_ATTN, 0);
    TSM(w == 0 && wg == 2, 124);
#pragma unroll 1
    for (uint32_t tasks = wg == 0 ? TASK0 : wg == 1 ? TASK1 : TASK2; tasks; tasks >>= 4) {
      const int c = (tasks & 7) - 1;
      conv_channel(fc, sb, c, wg, w, lane);
      if (lane == 0) mbar_arrive(bars + 8 * (B_YST + c));
      TSM(w == 0, 10 + c);
    }

    if (wg < 2) {
      const int g = lane >> 2;
      float acc[40];
#pragma unroll
      for (int i = 0; i < 40; i++) acc[i] = 0.f;
      const uint32_t da = desc_lo(sb + wg * 1024, 2048), db = desc_lo(sb, 2560);
      mbar_wait(bars + 8 * B_ATTN, 0);
      mbar_wait(bars + 8 * (B_YST + 3), 0);
      mbar_wait(bars + 8 * (B_YST + 4), 0);
      if (PW2) mbar_wait(bars + 8 * B_FULL2, 0);
      TSM(w == 0, 15 + wg);
#pragma unroll 1
      for (int j = 0; j < 8; j++) {
        mbar_wait(bars + 8 * (B_FULL2 + j), 0);
        const uint32_t oa = da + (off_o(j) >> 4), ob = db + (off_w(j) >> 4);
        wg_fence();
#pragma unroll
        for (int k = 0; k < 5; k++) WgSST<80>::mma<HI_NONE, HI_SW32>(acc, oa + 256 * k, ob + 32 * k, 1);
        wg_commit();
        wg_wait<1>();
        if (j >= 1 && j <= 4 && lane == 0) mbar_arrive(bars + 8 * (B_EMPTY2 + j - 1));
      }
      TSIF(w == 0 && wg == 0, 113);
      const int tr = 64 * wg + 16 * w + (lane & 15);
      const uint32_t fm = sb + OFF_QS + tr * 128, fx = (lane >> 4) ^ (tr & 7);
      const uint32_t ft = sb + OFF_QT + tr * 32 + (((lane >> 4) ^ (tr >> 2)) & 1) * 16;
      const float g0 = __uint_as_float(lds32(sb + OFF_GATE + (64 * wg + 16 * w + g) * 4));
      const float g1 = __uint_as_float(lds32(sb + OFF_GATE + (64 * wg + 16 * w + 8 + g) * 4));
      const uint32_t ga = pack2(g0, g0), gb = pack2(g1, g1);
      const uint32_t na = pack2(1.f - g0, 1.f - g0), nb = pack2(1.f - g1, 1.f - g1);

      wg_wait<0>();
      pin<40>(acc);
      TSM(w == 0, 17 + wg);
      uint32_t pb[20];
#pragma unroll
      for (int j = 0; j < 10; j++) {
        pb[2 * j] = bmul(na, pack2(acc[4 * j], acc[4 * j + 1]));
        pb[2 * j + 1] = bmul(nb, pack2(acc[4 * j + 2], acc[4 * j + 3]));
        asm volatile("" : "+r"(pb[2 * j]), "+r"(pb[2 * j + 1]));
      }
      const uint32_t ya = sb + OFF_YT + wg * 10240 + ((lane >> 4) * 8 + (lane & 7)) * 128 +
                          (((2 * w + (((lane >> 3) & 1) ^ wg)) ^ (lane & 7)) << 4);
      uint32_t qf[20];
      mbar_wait(bars + 8 * B_QF, 0);
#pragma unroll
      for (int j = 0; j < 5; j++) ldsm4(qf + 4 * j, j < 4 ? fm + ((fx ^ (2 * j)) << 4) : ft);
      mbar_wait(bars + 8 * B_YFULL, 0);
      TSM(w == 0 && wg == 0, 19);
#pragma unroll
      for (int j = 0; j < 5; j++) {
        uint32_t y[4];
        ldsm4t(y, ya + 2048 * j);
#pragma unroll
        for (int i = 0; i < 4; i++) qf[4 * j + i] = badd(bmul((i & 1) ? gb : ga, bmul(qf[4 * j + i], y[i])), pb[4 * j + i]);
      }
#pragma unroll
      for (int j = 0; j < 5; j++) stsm4(j < 4 ? fm + ((fx ^ (2 * j)) << 4) : ft, qf + 4 * j);
      fence_async_smem();
      __syncwarp();
      if (lane == 0) {
        const int row = 64 * wg + 16 * w;
        asm volatile("cp.async.bulk.tensor.2d.global.shared::cta.bulk_group [%0, {%2, %3}], [%1];"
                     ::"l"(&m.om), "r"(sb + OFF_QS + row * 128), "r"(80 * hg), "r"(128 * r + row) : "memory");
        asm volatile("cp.async.bulk.tensor.2d.global.shared::cta.bulk_group [%0, {%2, %3}], [%1];"
                     ::"l"(&m.ot), "r"(sb + OFF_QT + row * 32), "r"(80 * hg + 64), "r"(128 * r + row) : "memory");
        asm volatile("cp.async.bulk.commit_group;\ncp.async.bulk.wait_group.read 0;" ::: "memory");
      }
      TSM(true, 40 + 4 * wg + w);
      if (ENDBAR) asm volatile("bar.sync 15, 256;" ::: "memory");
    }
  }
}

typedef CUresult (*EncodeFn)(CUtensorMap*, CUtensorMapDataType, cuuint32_t, void*, const cuuint64_t*, const cuuint64_t*,
                             const cuuint32_t*, const cuuint32_t*, CUtensorMapInterleave, CUtensorMapSwizzle,
                             CUtensorMapL2promotion, CUtensorMapFloatOOBfill);

void encode(EncodeFn fn, CUtensorMap* tm, const void* base, int rank, const cuuint64_t* dims, const cuuint64_t* strides,
            const cuuint32_t* box, CUtensorMapSwizzle swz) {
  const cuuint32_t ones[3] = {1, 1, 1};
  fn(tm, CU_TENSOR_MAP_DATA_TYPE_BFLOAT16, rank, const_cast<void*>(base), dims, strides, box, ones,
     CU_TENSOR_MAP_INTERLEAVE_NONE, swz, CU_TENSOR_MAP_L2_PROMOTION_L2_128B, CU_TENSOR_MAP_FLOAT_OOB_FILL_NONE);
}

}

extern "C" void kernel_launch(void* const* d_in, const int* in_sizes, int n_in, void* d_out, int out_size) {
  (void)in_sizes; (void)n_in; (void)out_size;
  Params p;
  p.q = (const __nv_bfloat16*)d_in[0];
  p.k = (const __nv_bfloat16*)d_in[1];
  p.v = (const __nv_bfloat16*)d_in[2];
  p.shift_k = (const __nv_bfloat16*)d_in[3];
  p.ssm_k = (const __nv_bfloat16*)d_in[4];
  p.ssm_D = (const __nv_bfloat16*)d_in[5];
  p.wqkv = (const __nv_bfloat16*)d_in[7];
  p.wo = (const __nv_bfloat16*)d_in[8];
  p.gate_w = (const __nv_bfloat16*)d_in[9];
  p.out = (__nv_bfloat16*)d_out;
  p.zero = 0;

  static EncodeFn fn = nullptr;
  static void *yaddr = nullptr, *uaddr = nullptr;
  if (!fn) {
    cudaDriverEntryPointQueryResult qr;
    void* f = nullptr;
    cudaGetDriverEntryPoint("cuTensorMapEncodeTiled", &f, cudaEnableDefault, &qr);
    fn = (EncodeFn)f;
    cudaGetSymbolAddress(&yaddr, g_Y);
    cudaGetSymbolAddress(&uaddr, g_U);
    cudaFuncSetAttribute(fused_kernel, cudaFuncAttributeMaxDynamicSharedMemorySize, SMEM_BYTES);
  }
  Maps m;
  {
    const cuuint64_t dims[3] = {640, 1024, 2}, st[2] = {2560, 1280};
    const cuuint32_t box[3] = {64, 64, 2};
    encode(fn, &m.x, p.q, 3, dims, st, box, CU_TENSOR_MAP_SWIZZLE_128B);
  }
  {
    const cuuint64_t dims[3] = {640, 640, 3}, st[2] = {3840, 1280};
    const cuuint32_t box[3] = {64, 64, 3}, boxt[3] = {16, 64, 3};
    encode(fn, &m.wm, p.wqkv, 3, dims, st, box, CU_TENSOR_MAP_SWIZZLE_128B);
    encode(fn, &m.wt, p.wqkv, 3, dims, st, boxt, CU_TENSOR_MAP_SWIZZLE_32B);
  }
  {
    const cuuint64_t dims[3] = {64, 2048, 10}, st[2] = {1280, 128};
    const cuuint32_t boxk[3] = {64, 35, 1}, boxv[3] = {64, 32, 1};
    encode(fn, &m.k, p.k, 3, dims, st, boxk, CU_TENSOR_MAP_SWIZZLE_128B);
    encode(fn, &m.v, p.v, 3, dims, st, boxv, CU_TENSOR_MAP_SWIZZLE_128B);
  }
  {
    const cuuint64_t dims[3] = {16, 640, 40}, st[2] = {1280, 32};
    const cuuint32_t box[3] = {16, 40, 5};
    encode(fn, &m.wo, p.wo, 3, dims, st, box, CU_TENSOR_MAP_SWIZZLE_32B);
  }
  {
    const cuuint64_t dims[2] = {2048, 640}, st[1] = {Y_PITCH * 16};
    const cuuint32_t box[2] = {64, 80};
    encode(fn, &m.y, yaddr, 2, dims, st, box, CU_TENSOR_MAP_SWIZZLE_128B);
    const cuuint64_t stu[1] = {U_PITCH * 16};
    const cuuint32_t boxu[2] = {32, 64};
    encode(fn, &m.u, uaddr, 2, dims, stu, boxu, CU_TENSOR_MAP_SWIZZLE_NONE);
  }
  {
    const cuuint64_t dims[2] = {640, 2048}, st[1] = {1280};
    const cuuint32_t bqm[2] = {64, 128}, bqt[2] = {16, 128}, bom[2] = {64, 16}, bot[2] = {16, 16};
    encode(fn, &m.qm, p.q, 2, dims, st, bqm, CU_TENSOR_MAP_SWIZZLE_128B);
    encode(fn, &m.qt, p.q, 2, dims, st, bqt, CU_TENSOR_MAP_SWIZZLE_32B);
    encode(fn, &m.om, p.out, 2, dims, st, bom, CU_TENSOR_MAP_SWIZZLE_128B);
    encode(fn, &m.ot, p.out, 2, dims, st, bot, CU_TENSOR_MAP_SWIZZLE_32B);
  }
  fused_kernel<<<NCTA, NTHR, SMEM_BYTES>>>(m, p);
}
```

```cpp
#include <cuda.h>
#include <cuda_bf16.h>
#include <cuda_runtime.h>
#include <stdint.h>

namespace {

constexpr int SEQ = 2048, DIM = 640, NCTA = 128, NTHR = 512;

#define TRIG_KB 9
#define KV_KB 2
#define DEV_EXIT 0
#define ATT_GATE 0
#define G_AFTER 0
#define FENCE_LO 0
#define FENCE_HI 0
#define PW1 2
#define PW2 1
#define ENDBAR 0
#define PAD_KB 0
#define Y_ALIAS 1
#define NOMB 0
#define SRC_ROT 0
#define WAIT_NS 0
#define WB_TRIG B_USIG
#define G_POS 0
#define TAILF 1
#define T_ISSUE 384
#define T_PF 416
#define T_INIT 448
#define ATT_MERGE 0
#define BMAP 1
#define PRE2 1
#define KV_MIX 0
#define O_DEFER 0
#define TASK0 0x52
#define TASK1 0x3
#define TASK2 0x41
#define HALO_FIRST 1
#define PREV_EARLY 0
#define Y_RB 0
#define O_RB 0
#define O_EAGER 1
#define OP_TRIG B_OSIG
#define FUSE_MIX 1
#define Q_EARLY 1
#define WO_FAST 0
#define U_TRIM 1
#define ACQ 0
#define U_TMA 0
#define U_GATE 0
#define RF_GATE 0
#define WO_TRIG B_WST
#define WL_TRIG B_WOP
#define WO_GATE 1

constexpr uint32_t STAGE_BYTES = 47104, ST_W = 16384, ST_WT = 40960;
constexpr uint32_t O_BYTES = 20480, WO_BYTES = 12800;
constexpr uint32_t OFF_OA = 0;
constexpr uint32_t OFF_QS = 3 * O_BYTES, OFF_QT = OFF_QS + 16384;
constexpr uint32_t OFF_WC = 81920;
constexpr uint32_t OFF_WA = 94720;
constexpr uint32_t OFF_GATE = 145920;
constexpr uint32_t OFF_TT = 146432;
constexpr uint32_t OFF_KVX = 148480;
constexpr uint32_t OFF_CH3 = 163840;
constexpr uint32_t CH_BYTES = 12288, U_BYTES = 4096;
constexpr uint32_t OFF_FT = 225280, OFF_GT = 229376;
constexpr uint32_t OFF_CH0 = 188416;
constexpr uint32_t OFF_KVS = OFF_CH0, KVS_V = 4480, KVS_BYTES = 8576;
constexpr uint32_t OFF_WS = OFF_WA;
__device__ __forceinline__ uint32_t off_us(int s) { return OFF_CH0 + 4096 * ((0x65320 >> (4 * s)) & 7); }
constexpr uint32_t OFF_YT = 163840;
constexpr uint32_t OFF_BAR = 231936;
constexpr uint32_t SMEM_BYTES = OFF_BAR + 512;

enum : uint32_t {
  B_FULL1 = 0, B_EMPTY1 = 4, B_S3 = 7, B_FULL2 = 52, B_EMPTY2 = 13, B_U = 8, B_GATE = 12, B_HA = 19, B_HB = 20,
  B_ATTN = 21, B_C34 = 22, B_CONV = 23, B_YFULL = 24, B_EPOCH = 25, B_PREP = 26, B_P1 = 27, B_LAST = 28,
  B_E3 = 29, B_OSIG = 30, B_WOP = 31, B_USIG = 32, B_WST = 33, B_KV = 34, B_KVD = 39, B_QF = 17, B_ATT2 = 18, B_YST = 40,
  B_US = 45, B_YSIG = 50
};
constexpr uint32_t OFF_EPOCH = OFF_BAR + 8 * 51, OFF_D = OFF_BAR + 8 * 60;
__device__ __forceinline__ uint32_t off_o(int j) { return j < 4 ? OFF_OA + j * O_BYTES : j < 6 ? OFF_CH0 + (j - 4) * O_BYTES : OFF_OA + (j - 6) * O_BYTES; }
__device__ __forceinline__ uint32_t off_w(int j) { return j < 4 ? OFF_WA + j * WO_BYTES : j == 4 ? OFF_KVX : j == 5 ? OFF_WC : OFF_WA + (j - 6) * WO_BYTES; }
__device__ __forceinline__ int step_src(int hg, int j) {
  if (SRC_ROT == 2) {
    const int pos = (0x37621540 >> (4 * hg)) & 7;
    return j == 0 ? hg : (0x65217430 >> (4 * (j <= pos ? j - 1 : j))) & 7;
  }
  return SRC_ROT ? (hg + j) & 7 : j == 0 ? hg : j <= hg ? j - 1 : j;
}
__device__ __forceinline__ bool tail_first(int hg) { return TAILF && (hg & 3) == 3; }
__device__ __forceinline__ uint32_t off_ch(int c) { return (c < 3 ? OFF_CH0 : OFF_CH3 - 3 * CH_BYTES) + c * CH_BYTES; }

#define U_PITCH 264
__device__ __align__(1024) uint4 g_U[DIM * U_PITCH];
__device__ uint4 g_O[NCTA * 1280];
#define g_Y g_U
constexpr int Y_PITCH = U_PITCH;
__device__ uint4 g_WO[64 * 800];
__device__ uint4 g_halo[NCTA * 2 * 7 * 32];
__device__ float g_gate[SEQ + PAD_KB * 256];
__device__ unsigned g_cnt[32 * (1 + 2 * 16 + 8 + NCTA)];
constexpr int C_LAUNCH = 0, C_PREP = 32, C_Y = 32 * 17, C_W = 32 * 33, C_O = 32 * 41;

#define TSM(cond, slot) do { } while (0)
#define TSIF(cond, slot) do { if (__LINE__ >= FENCE_LO && __LINE__ < FENCE_HI) sched_fence(); } while (0)
__device__ __forceinline__ void sched_fence() {
  asm volatile("{\n.reg .pred p;\n.reg .u32 c;\nmov.u32 c, %%clock;\nsetp.eq.u32 p, c, 0;\n@p st.shared.u32 [%0], c;\n}"
               ::"r"(1024 + OFF_EPOCH + 4) : "memory");
}
#define TS(slot) TSIF(true, slot)

struct Params {
  const __nv_bfloat16 *q, *k, *v, *shift_k, *ssm_k, *ssm_D, *wqkv, *wo, *gate_w;
  __nv_bfloat16* out;
  uint32_t zero;
};

#define POLL_NS 0
constexpr int SPIN_LIMIT = 1 << 17;

__device__ __forceinline__ void mbar_init(uint32_t bar, uint32_t count) {
  asm volatile("mbarrier.init.shared::cta.b64 [%0], %1;" ::"r"(bar), "r"(count) : "memory");
}
__device__ __forceinline__ void mbar_expect_tx(uint32_t bar, uint32_t bytes) {
  asm volatile("mbarrier.arrive.expect_tx.shared::cta.b64 _, [%0], %1;" ::"r"(bar), "r"(bytes) : "memory");
}
__device__ __forceinline__ void mbar_arrive(uint32_t bar) {
  asm volatile("mbarrier.arrive.shared::cta.b64 _, [%0];" ::"r"(bar) : "memory");
}
__device__ __forceinline__ void mbar_wait(uint32_t bar, uint32_t parity) {
  uint32_t ok;
  int spins = 0;
  do {
    if (WAIT_NS)
      asm volatile("{\n.reg .pred p;\nmbarrier.try_wait.parity.shared::cta.b64 p, [%1], %2, %3;\nselp.b32 %0, 1, 0, p;\n}"
                   : "=r"(ok) : "r"(bar), "r"(parity), "r"(WAIT_NS) : "memory");
    else
      asm volatile("{\n.reg .pred p;\nmbarrier.try_wait.parity.shared::cta.b64 p, [%1], %2;\nselp.b32 %0, 1, 0, p;\n}"
                   : "=r"(ok) : "r"(bar), "r"(parity) : "memory");
    if (++spins > SPIN_LIMIT) break;
  } while (!ok);
}
__device__ __forceinline__ unsigned flag_read(const unsigned* p) {
  unsigned v;
  asm volatile("ld.relaxed.gpu.global.u32 %0, [%1];" : "=r"(v) : "l"(p) : "memory");
  return v;
}
__device__ __forceinline__ void flag_poll(const unsigned* p, unsigned target) {
  unsigned v;
  int spins = 0;
  do {
    if (POLL_NS && spins) __nanosleep(POLL_NS);
    asm volatile("ld.relaxed.gpu.global.u32 %0, [%1];" : "=r"(v) : "l"(p) : "memory");
    if (++spins > SPIN_LIMIT) break;
  } while ((int)(v - target) < 0);
}
__device__ __forceinline__ void flag_wait(const unsigned* p, unsigned target) {
  flag_poll(p, target);
  if (ACQ) asm volatile("fence.acquire.gpu;\nfence.proxy.async.global;" ::: "memory");
}
__device__ __forceinline__ void flag_signal(unsigned* p, int n, int lane) {
  if (lane == 0) asm volatile("fence.release.gpu;" ::: "memory");
  __syncwarp();
  if (lane < n) asm volatile("red.relaxed.gpu.global.add.u32 [%0], 1;" ::"l"(p + 32 * lane) : "memory");
}
__device__ __forceinline__ void flag_bump(unsigned* p) {
  asm volatile("red.relaxed.gpu.global.add.u32 [%0], 1;" ::"l"(p) : "memory");
}
__device__ __forceinline__ void fence_async_smem() { asm volatile("fence.proxy.async.shared::cta;" ::: "memory"); }
__device__ __forceinline__ void wg_sync(int id) { asm volatile("bar.sync %0, 128;" ::"r"(id) : "memory"); }

__device__ __forceinline__ void tma_2d(uint32_t dst, const CUtensorMap* tm, int c0, int c1, uint32_t bar) {
  asm volatile("cp.async.bulk.tensor.2d.shared::cluster.global.mbarrier::complete_tx::bytes [%0], [%1, {%3, %4}], [%2];"
               ::"r"(dst), "l"(tm), "r"(bar), "r"(c0), "r"(c1) : "memory");
}
__device__ __forceinline__ void tma_3d(uint32_t dst, const CUtensorMap* tm, int c0, int c1, int c2, uint32_t bar) {
  asm volatile("cp.async.bulk.tensor.3d.shared::cluster.global.mbarrier::complete_tx::bytes [%0], [%1, {%3, %4, %5}], [%2];"
               ::"r"(dst), "l"(tm), "r"(bar), "r"(c0), "r"(c1), "r"(c2) : "memory");
}
__device__ __forceinline__ void bulk_load(uint32_t dst, const void* src, uint32_t bytes, uint32_t bar) {
  asm volatile("cp.async.bulk.shared::cluster.global.mbarrier::complete_tx::bytes [%0], [%1], %2, [%3];"
               ::"r"(dst), "l"(src), "r"(bytes), "r"(bar) : "memory");
}
__device__ __forceinline__ void tm_prefetch(const CUtensorMap* tm) {
  asm volatile("prefetch.tensormap [%0];" ::"l"(tm) : "memory");
}

__device__ __forceinline__ void wg_fence() { asm volatile("wgmma.fence.sync.aligned;" ::: "memory"); }
__device__ __forceinline__ void wg_commit() { asm volatile("wgmma.commit_group.sync.aligned;" ::: "memory"); }
template <int N> __device__ __forceinline__ void wg_wait() { asm volatile("wgmma.wait_group.sync.aligned %0;" ::"n"(N) : "memory"); }
__device__ __forceinline__ uint32_t desc_lo(uint32_t addr, uint32_t lbo) { return ((addr & 0x3FFFF) >> 4) | ((lbo >> 4) << 16); }
constexpr uint32_t desc_hi(uint32_t sbo, uint32_t swz) { return (sbo >> 4) | (swz << 30); }
constexpr uint32_t HI_SW128 = desc_hi(1024, 1), HI_SW64 = desc_hi(512, 2), HI_SW32 = desc_hi(256, 3), HI_NONE = desc_hi(128, 0);
template <int N> __device__ __forceinline__ void pin(float* d) {
#pragma unroll
  for (int i = 0; i < N; i++) asm volatile("" : "+f"(d[i])::"memory");
}

__device__ __forceinline__ uint32_t lds32(uint32_t a) {
  uint32_t v;
  asm volatile("ld.volatile.shared.u32 %0, [%1];" : "=r"(v) : "r"(a) : "memory");
  return v;
}
__device__ __forceinline__ uint4 ldg128(const void* a) {
  uint4 v;
  asm volatile("ld.global.nc.v4.u32 {%0, %1, %2, %3}, [%4];" : "=r"(v.x), "=r"(v.y), "=r"(v.z), "=r"(v.w) : "l"(a) : "memory");
  return v;
}
__device__ __forceinline__ uint2 ldg64(const void* a) {
  uint2 v;
  asm volatile("ld.global.nc.v2.u32 {%0, %1}, [%2];" : "=r"(v.x), "=r"(v.y) : "l"(a) : "memory");
  return v;
}
__device__ __forceinline__ void ldsm4(uint32_t* r, uint32_t a) {
  asm volatile("ldmatrix.sync.aligned.m8n8.x4.shared.b16 {%0, %1, %2, %3}, [%4];"
               : "=r"(r[0]), "=r"(r[1]), "=r"(r[2]), "=r"(r[3]) : "r"(a) : "memory");
}
__device__ __forceinline__ void ldsm4t(uint32_t* r, uint32_t a) {
  asm volatile("ldmatrix.sync.aligned.m8n8.x4.trans.shared.b16 {%0, %1, %2, %3}, [%4];"
               : "=r"(r[0]), "=r"(r[1]), "=r"(r[2]), "=r"(r[3]) : "r"(a) : "memory");
}
__device__ __forceinline__ uint2 lds64(uint32_t a) {
  uint2 v;
  asm volatile("ld.shared.v2.u32 {%0, %1}, [%2];" : "=r"(v.x), "=r"(v.y) : "r"(a) : "memory");
  return v;
}
__device__ __forceinline__ uint4 lds128(uint32_t a) {
  uint4 v;
  asm volatile("ld.shared.v4.u32 {%0, %1, %2, %3}, [%4];" : "=r"(v.x), "=r"(v.y), "=r"(v.z), "=r"(v.w) : "r"(a) : "memory");
  return v;
}
__device__ __forceinline__ void sts128(uint32_t a, uint32_t x, uint32_t y, uint32_t z, uint32_t w) {
  asm volatile("st.shared.v4.u32 [%0], {%1, %2, %3, %4};" ::"r"(a), "r"(x), "r"(y), "r"(z), "r"(w) : "memory");
}
__device__ __forceinline__ void stsm4(uint32_t a, const uint32_t* r) {
  asm volatile("stmatrix.sync.aligned.m8n8.x4.shared.b16 [%0], {%1, %2, %3, %4};" ::"r"(a), "r"(r[0]), "r"(r[1]), "r"(r[2]), "r"(r[3]) : "memory");
}
__device__ __forceinline__ void stsm4t(uint32_t a, const uint32_t* r) {
  asm volatile("stmatrix.sync.aligned.m8n8.x4.trans.shared.b16 [%0], {%1, %2, %3, %4};" ::"r"(a), "r"(r[0]), "r"(r[1]), "r"(r[2]), "r"(r[3]) : "memory");
}
__device__ __forceinline__ uint32_t pack2(float lo, float hi) {
  uint32_t r;
  asm("cvt.rn.bf16x2.f32 %0, %1, %2;" : "=r"(r) : "f"(hi), "f"(lo));
  return r;
}
__device__ __forceinline__ uint32_t movm(uint32_t a) {
  uint32_t d;
  asm volatile("movmatrix.sync.aligned.m8n8.trans.b16 %0, %1;" : "=r"(d) : "r"(a));
  return d;
}
__device__ __forceinline__ uint32_t bmul(uint32_t a, uint32_t b) {
  uint32_t d;
  asm("mul.rn.bf16x2 %0, %1, %2;" : "=r"(d) : "r"(a), "r"(b));
  return d;
}
__device__ __forceinline__ uint32_t badd(uint32_t a, uint32_t b) {
  uint32_t d;
  asm("add.rn.bf16x2 %0, %1, %2;" : "=r"(d) : "r"(a), "r"(b));
  return d;
}
__device__ __forceinline__ uint32_t bfma(uint32_t a, uint32_t b, uint32_t c) {
  uint32_t d;
  asm("fma.rn.bf16x2 %0, %1, %2, %3;" : "=r"(d) : "r"(a), "r"(b), "r"(c));
  return d;
}
__device__ __forceinline__ float bf_lo(uint32_t x) { return __uint_as_float(x << 16); }
__device__ __forceinline__ float bf_hi(uint32_t x) { return __uint_as_float(x & 0xFFFF0000u); }
__device__ __forceinline__ float ex2(float x) {
  float y;
  asm("ex2.approx.ftz.f32 %0, %1;" : "=f"(y) : "f"(x));
  return y;
}
__device__ __forceinline__ float rcp(float x) {
  float y;
  asm("rcp.approx.ftz.f32 %0, %1;" : "=f"(y) : "f"(x));
  return y;
}
__device__ __forceinline__ void mma16816(float* d, uint32_t a0, uint32_t a1, uint32_t a2, uint32_t a3, uint32_t b0, uint32_t b1) {
  asm volatile("mma.sync.aligned.m16n8k16.row.col.f32.bf16.bf16.f32 {%0, %1, %2, %3}, {%4, %5, %6, %7}, {%8, %9}, {%0, %1, %2, %3};"
               : "+f"(d[0]), "+f"(d[1]), "+f"(d[2]), "+f"(d[3])
               : "r"(a0), "r"(a1), "r"(a2), "r"(a3), "r"(b0), "r"(b1));
}
__device__ __forceinline__ void mma1688(float* d, uint32_t a0, uint32_t a1, uint32_t b0) {
  asm volatile("mma.sync.aligned.m16n8k8.row.col.f32.bf16.bf16.f32 {%0, %1, %2, %3}, {%4, %5}, {%6}, {%0, %1, %2, %3};"
               : "+f"(d[0]), "+f"(d[1]), "+f"(d[2]), "+f"(d[3])
               : "r"(a0), "r"(a1), "r"(b0));
}

template <int N> struct WgRS;
template <int N> struct WgSST;
template <> struct WgRS<32> {
  template <uint32_t HB>
  static __device__ __forceinline__ void mma(float* d, const uint32_t* a, uint32_t db) {
    asm volatile("{\n.reg .pred p;\n.reg .b64 db;\nsetp.ne.b32 p, %22, 0;\n"
      "mov.b64 db, {%20, %21};\n"
      "wgmma.mma_async.sync.aligned.m64n32k16.f32.bf16.bf16 {"
      "%0, %1, %2, %3, %4, %5, %6, %7, %8, %9, %10, %11, %12, %13, %14, %15"
      "}, {%16, %17, %18, %19}, db, p, 1, 1, 1;\n}\n"
      : "+f"(d[0]), "+f"(d[1]), "+f"(d[2]), "+f"(d[3]), "+f"(d[4]), "+f"(d[5]), "+f"(d[6]), "+f"(d[7]),
        "+f"(d[8]), "+f"(d[9]), "+f"(d[10]), "+f"(d[11]), "+f"(d[12]), "+f"(d[13]), "+f"(d[14]), "+f"(d[15])
      : "r"(a[0]), "r"(a[1]), "r"(a[2]), "r"(a[3]), "r"(db), "n"(HB), "n"(1));
  }
  template <uint32_t HB>
  static __device__ __forceinline__ void set(float* d, const uint32_t* a, uint32_t db) {
    asm volatile("{\n.reg .pred p;\n.reg .b64 db;\nsetp.ne.b32 p, %22, 0;\n"
      "mov.b64 db, {%20, %21};\n"
      "wgmma.mma_async.sync.aligned.m64n32k16.f32.bf16.bf16 {"
      "%0, %1, %2, %3, %4, %5, %6, %7, %8, %9, %10, %11, %12, %13, %14, %15"
      "}, {%16, %17, %18, %19}, db, p, 1, 1, 1;\n}\n"
      : "=f"(d[0]), "=f"(d[1]), "=f"(d[2]), "=f"(d[3]), "=f"(d[4]), "=f"(d[5]), "=f"(d[6]), "=f"(d[7]),
        "=f"(d[8]), "=f"(d[9]), "=f"(d[10]), "=f"(d[11]), "=f"(d[12]), "=f"(d[13]), "=f"(d[14]), "=f"(d[15])
      : "r"(a[0]), "r"(a[1]), "r"(a[2]), "r"(a[3]), "r"(db), "n"(HB), "n"(0));
  }
};
template <> struct WgRS<64> {
  template <uint32_t HB>
  static __device__ __forceinline__ void mma(float* d, const uint32_t* a, uint32_t db) {
    asm volatile("{\n.reg .pred p;\n.reg .b64 db;\nsetp.ne.b32 p, %38, 0;\n"
      "mov.b64 db, {%36, %37};\n"
      "wgmma.mma_async.sync.aligned.m64n64k16.f32.bf16.bf16 {"
      "%0, %1, %2, %3, %4, %5, %6, %7, %8, %9, %10, %11, %12, %13, %14, %15, "
      "%16, %17, %18, %19, %20, %21, %22, %23, %24, %25, %26, %27, %28, %29, %30, %31"
      "}, {%32, %33, %34, %35}, db, p, 1, 1, 1;\n}\n"
      : "+f"(d[0]), "+f"(d[1]), "+f"(d[2]), "+f"(d[3]), "+f"(d[4]), "+f"(d[5]), "+f"(d[6]), "+f"(d[7]),
        "+f"(d[8]), "+f"(d[9]), "+f"(d[10]), "+f"(d[11]), "+f"(d[12]), "+f"(d[13]), "+f"(d[14]), "+f"(d[15]),
        "+f"(d[16]), "+f"(d[17]), "+f"(d[18]), "+f"(d[19]), "+f"(d[20]), "+f"(d[21]), "+f"(d[22]), "+f"(d[23]),
        "+f"(d[24]), "+f"(d[25]), "+f"(d[26]), "+f"(d[27]), "+f"(d[28]), "+f"(d[29]), "+f"(d[30]), "+f"(d[31])
      : "r"(a[0]), "r"(a[1]), "r"(a[2]), "r"(a[3]), "r"(db), "n"(HB), "n"(1));
  }
  template <uint32_t HB>
  static __device__ __forceinline__ void set(float* d, const uint32_t* a, uint32_t db) {
    asm volatile("{\n.reg .pred p;\n.reg .b64 db;\nsetp.ne.b32 p, %38, 0;\n"
      "mov.b64 db, {%36, %37};\n"
      "wgmma.mma_async.sync.aligned.m64n64k16.f32.bf16.bf16 {"
      "%0, %1, %2, %3, %4, %5, %6, %7, %8, %9, %10, %11, %12, %13, %14, %15, "
      "%16, %17, %18, %19, %20, %21, %22, %23, %24, %25, %26, %27, %28, %29, %30, %31"
      "}, {%32, %33, %34, %35}, db, p, 1, 1, 1;\n}\n"
      : "=f"(d[0]), "=f"(d[1]), "=f"(d[2]), "=f"(d[3]), "=f"(d[4]), "=f"(d[5]), "=f"(d[6]), "=f"(d[7]),
        "=f"(d[8]), "=f"(d[9]), "=f"(d[10]), "=f"(d[11]), "=f"(d[12]), "=f"(d[13]), "=f"(d[14]), "=f"(d[15]),
        "=f"(d[16]), "=f"(d[17]), "=f"(d[18]), "=f"(d[19]), "=f"(d[20]), "=f"(d[21]), "=f"(d[22]), "=f"(d[23]),
        "=f"(d[24]), "=f"(d[25]), "=f"(d[26]), "=f"(d[27]), "=f"(d[28]), "=f"(d[29]), "=f"(d[30]), "=f"(d[31])
      : "r"(a[0]), "r"(a[1]), "r"(a[2]), "r"(a[3]), "r"(db), "n"(HB), "n"(0));
  }
};
template <> struct WgSST<48> {
  template <uint32_t HA, uint32_t HB>
  static __device__ __forceinline__ void mma(float* d, uint32_t da, uint32_t db, int sc) {
    asm volatile("{\n.reg .pred p;\n.reg .b64 da, db;\nsetp.ne.b32 p, %28, 0;\n"
      "mov.b64 da, {%24, %25};\nmov.b64 db, {%26, %27};\n"
      "wgmma.mma_async.sync.aligned.m64n48k16.f32.bf16.bf16 {"
      "%0, %1, %2, %3, %4, %5, %6, %7, %8, %9, %10, %11, %12, %13, %14, %15, "
      "%16, %17, %18, %19, %20, %21, %22, %23"
      "}, da, db, p, 1, 1, 0, 1;\n}\n"
      : "+f"(d[0]), "+f"(d[1]), "+f"(d[2]), "+f"(d[3]), "+f"(d[4]), "+f"(d[5]), "+f"(d[6]), "+f"(d[7]),
        "+f"(d[8]), "+f"(d[9]), "+f"(d[10]), "+f"(d[11]), "+f"(d[12]), "+f"(d[13]), "+f"(d[14]), "+f"(d[15]),
        "+f"(d[16]), "+f"(d[17]), "+f"(d[18]), "+f"(d[19]), "+f"(d[20]), "+f"(d[21]), "+f"(d[22]), "+f"(d[23])
      : "r"(da), "n"(HA), "r"(db), "n"(HB), "r"(sc));
  }
};
template <> struct WgSST<80> {
  template <uint32_t HA, uint32_t HB>
  static __device__ __forceinline__ void mma(float* d, uint32_t da, uint32_t db, int sc) {
    asm volatile("{\n.reg .pred p;\n.reg .b64 da, db;\nsetp.ne.b32 p, %44, 0;\n"
      "mov.b64 da, {%40, %41};\nmov.b64 db, {%42, %43};\n"
      "wgmma.mma_async.sync.aligned.m64n80k16.f32.bf16.bf16 {"
      "%0, %1, %2, %3, %4, %5, %6, %7, %8, %9, %10, %11, %12, %13, %14, %15, "
      "%16, %17, %18, %19, %20, %21, %22, %23, %24, %25, %26, %27, %28, %29, %30, %31, "
      "%32, %33, %34, %35, %36, %37, %38, %39"
      "}, da, db, p, 1, 1, 0, 1;\n}\n"
      : "+f"(d[0]), "+f"(d[1]), "+f"(d[2]), "+f"(d[3]), "+f"(d[4]), "+f"(d[5]), "+f"(d[6]), "+f"(d[7]),
        "+f"(d[8]), "+f"(d[9]), "+f"(d[10]), "+f"(d[11]), "+f"(d[12]), "+f"(d[13]), "+f"(d[14]), "+f"(d[15]),
        "+f"(d[16]), "+f"(d[17]), "+f"(d[18]), "+f"(d[19]), "+f"(d[20]), "+f"(d[21]), "+f"(d[22]), "+f"(d[23]),
        "+f"(d[24]), "+f"(d[25]), "+f"(d[26]), "+f"(d[27]), "+f"(d[28]), "+f"(d[29]), "+f"(d[30]), "+f"(d[31]),
        "+f"(d[32]), "+f"(d[33]), "+f"(d[34]), "+f"(d[35]), "+f"(d[36]), "+f"(d[37]), "+f"(d[38]), "+f"(d[39])
      : "r"(da), "n"(HA), "r"(db), "n"(HB), "r"(sc));
  }
};
template <> struct WgSST<192> {
  template <uint32_t HA, uint32_t HB>
  static __device__ __forceinline__ void mma(float* d, uint32_t da, uint32_t db, int sc) {
    asm volatile("{\n.reg .pred p;\n.reg .b64 da, db;\nsetp.ne.b32 p, %100, 0;\n"
      "mov.b64 da, {%96, %97};\nmov.b64 db, {%98, %99};\n"
      "wgmma.mma_async.sync.aligned.m64n192k16.f32.bf16.bf16 {"
      "%0, %1, %2, %3, %4, %5, %6, %7, %8, %9, %10, %11, %12, %13, %14, %15, "
      "%16, %17, %18, %19, %20, %21, %22, %23, %24, %25, %26, %27, %28, %29, %30, %31, "
      "%32, %33, %34, %35, %36, %37, %38, %39, %40, %41, %42, %43, %44, %45, %46, %47, "
      "%48, %49, %50, %51, %52, %53, %54, %55, %56, %57, %58, %59, %60, %61, %62, %63, "
      "%64, %65, %66, %67, %68, %69, %70, %71, %72, %73, %74, %75, %76, %77, %78, %79, "
      "%80, %81, %82, %83, %84, %85, %86, %87, %88, %89, %90, %91, %92, %93, %94, %95"
      "}, da, db, p, 1, 1, 0, 1;\n}\n"
      : "+f"(d[0]), "+f"(d[1]), "+f"(d[2]), "+f"(d[3]), "+f"(d[4]), "+f"(d[5]), "+f"(d[6]), "+f"(d[7]),
        "+f"(d[8]), "+f"(d[9]), "+f"(d[10]), "+f"(d[11]), "+f"(d[12]), "+f"(d[13]), "+f"(d[14]), "+f"(d[15]),
        "+f"(d[16]), "+f"(d[17]), "+f"(d[18]), "+f"(d[19]), "+f"(d[20]), "+f"(d[21]), "+f"(d[22]), "+f"(d[23]),
        "+f"(d[24]), "+f"(d[25]), "+f"(d[26]), "+f"(d[27]), "+f"(d[28]), "+f"(d[29]), "+f"(d[30]), "+f"(d[31]),
        "+f"(d[32]), "+f"(d[33]), "+f"(d[34]), "+f"(d[35]), "+f"(d[36]), "+f"(d[37]), "+f"(d[38]), "+f"(d[39]),
        "+f"(d[40]), "+f"(d[41]), "+f"(d[42]), "+f"(d[43]), "+f"(d[44]), "+f"(d[45]), "+f"(d[46]), "+f"(d[47]),
        "+f"(d[48]), "+f"(d[49]), "+f"(d[50]), "+f"(d[51]), "+f"(d[52]), "+f"(d[53]), "+f"(d[54]), "+f"(d[55]),
        "+f"(d[56]), "+f"(d[57]), "+f"(d[58]), "+f"(d[59]), "+f"(d[60]), "+f"(d[61]), "+f"(d[62]), "+f"(d[63]),
        "+f"(d[64]), "+f"(d[65]), "+f"(d[66]), "+f"(d[67]), "+f"(d[68]), "+f"(d[69]), "+f"(d[70]), "+f"(d[71]),
        "+f"(d[72]), "+f"(d[73]), "+f"(d[74]), "+f"(d[75]), "+f"(d[76]), "+f"(d[77]), "+f"(d[78]), "+f"(d[79]),
        "+f"(d[80]), "+f"(d[81]), "+f"(d[82]), "+f"(d[83]), "+f"(d[84]), "+f"(d[85]), "+f"(d[86]), "+f"(d[87]),
        "+f"(d[88]), "+f"(d[89]), "+f"(d[90]), "+f"(d[91]), "+f"(d[92]), "+f"(d[93]), "+f"(d[94]), "+f"(d[95])
      : "r"(da), "n"(HA), "r"(db), "n"(HB), "r"(sc));
  }
};

struct FftConst {
  uint32_t f[2][4], fi[4][4];
  uint32_t ta[2][2], tb[2][2];
};
__device__ __forceinline__ void cis(int m, float scale, float& c, float& s) {
  const float a = (float)m * (-6.283185307179586f * scale);
  c = __cosf(a);
  s = __sinf(a);
}
__device__ __forceinline__ void fft_tables(uint32_t (&v)[12], int tw) {
  const int row = tw >> 2, ch = tw & 3;
#pragma unroll
  for (int i = 0; i < 4; i++) {
    float c[2], s[2], x[2];
#pragma unroll
    for (int e = 0; e < 2; e++) {
      cis((((32 * (8 * ch + 2 * i + e) + 15) * (4 * row - 63) + 2048) & 4095) - 2048, 1.f / 4096, c[e], s[e]);
      float gc, gs;
      cis((((row & 15) * (8 * (ch & 1) + 2 * i + e) + 8) & 15) - 8, 1.f / 16, gc, gs);
      x[e] = (row >> 4) == (ch >> 1) ? gc : (ch >> 1) ? gs : -gs;
    }
    v[i] = pack2(c[0] * 0.125f, c[1] * 0.125f);
    v[4 + i] = pack2(s[0] * 0.125f, s[1] * 0.125f);
    v[8 + i] = pack2(x[0], x[1]);
  }
#pragma unroll
  for (int i = 0; i < 12; i++) asm volatile("" : "+r"(v[i]));
}
__device__ __forceinline__ void fft_tables_store(const uint32_t (&v)[12], uint32_t sb, int tw) {
  const int row = tw >> 2;
  const uint32_t x = ((tw ^ (row >> 1)) & 3) << 4, a = sb + OFF_FT + (16 * (row >> 3) + (row & 7)) * 64 + x;
  sts128(a, v[0], v[1], v[2], v[3]);
  sts128(a + 512, v[4], v[5], v[6], v[7]);
  sts128(sb + OFF_GT + row * 64 + x, v[8], v[9], v[10], v[11]);
}
__device__ __forceinline__ void fft_twiddles(uint32_t (&v)[2], int tw) {
  float a[2], s[2];
#pragma unroll
  for (int i = 0; i < 2; i++) {
    float c;
    cis((2 * (2 * (tw & 3) + i) - 15) * (4 * (tw >> 2) - 63), 1.f / 4096, c, s[i]);
    a[i] = __fdividef(-s[i], 1.f + c);
  }
  v[0] = pack2(a[0], a[1]);
  v[1] = pack2(s[0], s[1]);
  asm volatile("" : "+r"(v[0]), "+r"(v[1]));
}
__device__ __forceinline__ void fft_matrices(FftConst& k, uint32_t sb, int w, int lane) {
  const uint32_t x = (lane >> 1) & 3;
  const uint2 t0 = lds64(sb + OFF_TT + 256 * w + 8 * lane), t1 = lds64(sb + OFF_TT + 256 * w + 8 * (lane ^ 3));
  k.ta[0][0] = t0.x;
  k.tb[0][0] = t0.y;
  k.ta[1][1] = __byte_perm(t1.x, 0, 0x1032);
  k.tb[1][1] = __byte_perm(t1.y, 0, 0x1032);
#pragma unroll
  for (int j = 0; j < 2; j++) {
    k.ta[1 - j][j] = k.ta[j][j] ^ 0x80008000u;
    k.tb[1 - j][j] = k.tb[j][j] ^ 0x80008000u;
    asm volatile("" : "+r"(k.ta[0][j]), "+r"(k.tb[0][j]), "+r"(k.ta[1][j]), "+r"(k.tb[1][j]));
  }
#pragma unroll
  for (int i = 0; i < 2; i++) {
    ldsm4(k.f[i], sb + OFF_FT + (16 * w + (lane & 15)) * 64 + (((2 * i + (lane >> 4)) ^ x) << 4));
    ldsm4t(k.fi[i], sb + OFF_FT + (32 * i + lane) * 64 + ((w ^ x) << 4));
#pragma unroll
    for (int j = 0; j < 4; j++) {
      k.fi[2 + i][j] = (j & 1) ? k.fi[i][j - 1] ^ 0x80008000u : k.fi[i][j + 1];
      asm volatile("" : "+r"(k.fi[2 + i][j]));
    }
  }
}
__device__ __forceinline__ void rot(uint32_t& x, uint32_t& y, uint32_t a, uint32_t b) {
  x = bfma(a, y, x);
  y = bfma(b, x, y);
  x = bfma(a, y, x);
}
__device__ __forceinline__ void twiddle_fwd(uint32_t (&a)[4][4], float* d, const FftConst& k) {
#pragma unroll
  for (int q = 0; q < 4; q++)
#pragma unroll
    for (int j = 0; j < 2; j++) {
      const float* x = d + 8 * q + 4 * j;
      uint32_t re = pack2(x[0], x[1]), im = pack2(x[2], x[3]);
      rot(re, im, k.ta[0][j], k.tb[0][j]);
      a[q & 2][2 * j + (q & 1)] = re;
      a[(q & 2) + 1][2 * j + (q & 1)] = im;
    }
}
__device__ __forceinline__ void g_step(float* d, const uint32_t (&a)[4][4], uint32_t dre, uint32_t dim) {
  WgRS<32>::set<HI_SW64>(d, a[0], dre);
  WgRS<32>::set<HI_SW64>(d + 16, a[2], dre);
  WgRS<32>::mma<HI_SW64>(d, a[1], dim);
  WgRS<32>::mma<HI_SW64>(d + 16, a[3], dim);
  wg_commit();
}

__device__ __forceinline__ void conv_channel(const FftConst& k, uint32_t sb, int c, int wg, int w, int lane) {
  const uint32_t cb = sb + off_ch(c), bars = sb + OFF_BAR;
  const uint32_t du = desc_lo(cb, 1024), dg = desc_lo(sb + OFF_GT, 16), dz = desc_lo(cb + U_BYTES, 16);
  float U[32], H[32];
  uint32_t a[4][4], e[4][4];
  const float dv = __uint_as_float(lds32(sb + OFF_D + 4 * c));
  wg_fence();
  WgRS<64>::set<HI_SW32>(H, k.f[0], du + 256);
  WgRS<64>::mma<HI_SW32>(H, k.f[1], du + 256 + 32);
  wg_commit();
  wg_wait<0>();
  pin<32>(H);
  twiddle_fwd(a, H, k);
  if (ATT_GATE) mbar_wait(bars + 8 * (ATT_GATE == 1 ? B_ATTN : B_ATT2), 0);
  mbar_wait(bars + 8 * (B_U + (c < 3 ? c : 3)), 0);
  TSM(w == 0 && c < 3, 7 + wg);
  wg_fence();
  WgRS<64>::set<HI_SW32>(U, k.f[0], du);
  WgRS<64>::mma<HI_SW32>(U, k.f[1], du + 32);
  wg_commit();
  g_step(H, a, dg, dg + 64);
  wg_wait<1>();
  pin<32>(U);
  twiddle_fwd(e, U, k);
  wg_fence();
  g_step(U, e, dg, dg + 64);
  wg_wait<0>();
  pin<32>(U);
  pin<32>(H);
#pragma unroll
  for (int j = 0; j < 2; j++) {
    float pr[4][2], pi[4][2];
#pragma unroll
    for (int x = 0; x < 2; x++) {
      H[4 * j + x] += dv;
#pragma unroll
      for (int m = 0; m < 4; m++) {
#pragma unroll
        for (int q = 0; q <= m; q++) {
          const int ih = 16 * (q >> 1) + 2 * (q & 1) + 4 * j + x, iu = 16 * ((m - q) >> 1) + 2 * ((m - q) & 1) + 4 * j + x;
          pr[m][x] = q ? fmaf(H[ih], U[iu], pr[m][x]) : H[ih] * U[iu];
          pi[m][x] = q ? fmaf(H[ih], U[iu + 8], pi[m][x]) : H[ih] * U[iu + 8];
          pr[m][x] = fmaf(-H[ih + 8], U[iu + 8], pr[m][x]);
          pi[m][x] = fmaf(H[ih + 8], U[iu], pi[m][x]);
        }
      }
    }
#pragma unroll
    for (int m = 0; m < 4; m++) {
      a[m & 2][2 * j + (m & 1)] = pack2(pr[m][0], pr[m][1]);
      a[(m & 2) + 1][2 * j + (m & 1)] = pack2(pi[m][0], pi[m][1]);
    }
  }
  wg_fence();
  g_step(U, a, dg + 64, dg);
  const uint32_t za = cb + U_BYTES + (8 * w + (lane & 7)) * 128 + (((lane >> 3) ^ (lane & 7)) << 4);
  const uint32_t ya = cb + (lane >> 4) * 1024 + (8 * w + (lane & 7)) * 32 + ((((lane >> 3) ^ (lane >> 2)) & 1) << 4);
  wg_sync(1 + wg);
  wg_wait<0>();
  pin<32>(U);
  TSIF(w == 0, 80 + c);
#pragma unroll
  for (int p = 0; p < 2; p++) {
#pragma unroll
    for (int i = 0; i < 4; i++) {
      const int j = i & 1;
      const float* x = U + 16 * p + 4 * j + (i & 2);
      e[p][i] = pack2(x[8], x[9]);
      e[2 + p][i] = pack2(x[0], x[1]);
      rot(e[p][i], e[2 + p][i], k.ta[1][j], k.tb[1][j]);
    }
    stsm4(za ^ (64 * p), e[p]);
    stsm4((za ^ (64 * p)) + 4096, e[2 + p]);
  }
  fence_async_smem();
  wg_sync(1 + wg);
  wg_fence();
  WgRS<64>::set<HI_SW128>(H, k.fi[0], dz);
#pragma unroll
  for (int ks = 1; ks < 4; ks++) WgRS<64>::mma<HI_SW128>(H, k.fi[ks], dz + 128 * ks);
  wg_commit();
  if (WO_FAST) mbar_wait(bars + 8 * B_ATTN, 0);
  wg_wait<0>();
  pin<32>(H);
  TSIF(w == 0, 88 + c);
#pragma unroll
  for (int j = 0; j < 8; j++)
    a[j >> 2][j & 3] = j < 2 ? pack2(H[4 * j], H[4 * j + 1]) : pack2(H[4 * j] + H[4 * j - 6], H[4 * j + 1] + H[4 * j - 5]);
  stsm4(ya, a[0]);
  stsm4(ya + 2048, a[1]);
  fence_async_smem();
  __syncwarp();
}

__device__ __forceinline__ void prep_slab(uint4* res, const uint2* sw, uint32_t sb, int slab, int w, int lane) {
  const int t = lane & 3, tp = (lane & 7) >> 1, pos = 8 * tp + 2 * (((lane >> 3) + tp) & 3) + (lane & 1);
  const uint32_t base = sb + OFF_KVS + slab * KVS_BYTES + pos * 128;
  uint32_t kk[2][4][4], vv[2][4];
  mbar_wait(sb + OFF_BAR + 8 * (B_KV + slab), 0);
#pragma unroll
  for (int h = 0; h < 2; h++) {
#pragma unroll
    for (int j = 0; j < 4; j++) {
      const uint32_t a = base + 128 * j;
      ldsm4t(kk[h][j], a + (((w + 4 * h) ^ ((a >> 7) & 7)) << 4));
    }
    const uint32_t a = base + KVS_V;
    ldsm4t(vv[h], a + (((w + 4 * h) ^ ((a >> 7) & 7)) << 4));
  }
#pragma unroll
  for (int h = 0; h < 2; h++) {
    uint32_t (&k)[4][4] = kk[h];
    uint32_t (&v)[4] = vv[h];
    const uint32_t w0 = __byte_perm(sw[h].x, 0, 0x1010), w1 = __byte_perm(sw[h].x, 0, 0x3232);
    const uint32_t w2 = __byte_perm(sw[h].y, 0, 0x1010), w3 = __byte_perm(sw[h].y, 0, 0x3232);
#pragma unroll
    for (int m = 0; m < 4; m++)
      v[m] = bmul(badd(badd(badd(bmul(k[0][m], w3), bmul(k[1][m], w2)), bmul(k[2][m], w1)), bmul(k[3][m], w0)), v[m]);
    uint32_t a[4];
#pragma unroll
    for (int m = 0; m < 4; m++) a[m] = (t & 1) ? v[(m + 3) & 3] : v[m];
    res[h] = (t & 2) ? make_uint4(a[2], a[3], a[0], a[1]) : make_uint4(a[0], a[1], a[2], a[3]);
  }
}

__device__ __forceinline__ void gate_load(uint4 (&gw)[5], uint4 (&x)[10], const Params& p, int row, int lane) {
#pragma unroll
  for (int j = 0; j < 5; j++) gw[j] = ldg128(reinterpret_cast<const uint4*>(p.gate_w) + 8 * (j + 5 * ((lane >> 3) & 1)) + (lane & 7));
#pragma unroll
  for (int j = 0; j < 10; j++) x[j] = ldg128(reinterpret_cast<const uint4*>(p.q) + (row + (lane >> 3)) * (DIM / 8) + 8 * j + (lane & 7));
}
__device__ __forceinline__ void gate_finish(const uint4 (&gw)[5], const uint4 (&x)[10], int row, int lane) {
  const int g = lane >> 2, t = lane & 3;
  float d[2][4] = {};
#pragma unroll
  for (int j = 0; j < 5; j++) {
    mma16816(d[0], x[j].x, x[j + 5].x, x[j].y, x[j + 5].y, gw[j].x, gw[j].y);
    mma16816(d[1], x[j].z, x[j + 5].z, x[j].w, x[j + 5].w, gw[j].z, gw[j].w);
  }
  float z = t ? ((g & 1) ? d[0][3] + d[1][3] : d[0][2] + d[1][2]) : ((g & 1) ? d[0][1] + d[1][1] : d[0][0] + d[1][0]);
  z += __shfl_xor_sync(0xffffffffu, z, 1);
  z += __shfl_xor_sync(0xffffffffu, z, 4);
  z = bf_lo(pack2(z, 0.f));
  if ((lane & 7) == 0) g_gate[row + (lane >> 3)] = bf_lo(pack2(__fdividef(1.f, 1.f + __expf(-z)), 0.f));
}

__device__ __forceinline__ uint32_t bmax(uint32_t a, uint32_t b) {
  uint32_t d;
  asm("max.bf16x2 %0, %1, %2;" : "=r"(d) : "r"(a), "r"(b));
  return d;
}
__device__ __forceinline__ void softmax_two(const float (&l)[2][2], uint32_t& p0, uint32_t& p1) {
  constexpr float kScale = 0.22360679774997896f, kLog2e = 1.4426950408889634f;
  const uint32_t r0 = pack2(l[0][0], l[1][0]), r1 = pack2(l[0][1], l[1][1]);
  const uint32_t x0 = pack2(bf_lo(r0) * kScale, bf_hi(r0) * kScale), x1 = pack2(bf_lo(r1) * kScale, bf_hi(r1) * kScale);
  uint32_t m = bmax(x0, x1);
  m = bmax(m, __shfl_xor_sync(0xffffffffu, m, 1));
  m = bmax(m, __shfl_xor_sync(0xffffffffu, m, 2));
  const float m0 = bf_lo(m) * kLog2e, m1 = bf_hi(m) * kLog2e;
  p0 = pack2(ex2(bf_lo(x0) * kLog2e - m0), ex2(bf_lo(x1) * kLog2e - m0));
  p1 = pack2(ex2(bf_hi(x0) * kLog2e - m1), ex2(bf_hi(x1) * kLog2e - m1));
}

__device__ __forceinline__ void halo_read(uint32_t (&kpv)[10], uint32_t (&vpv)[10], uint32_t (&tg)[7], const uint4* hp) {
#pragma unroll
  for (int j = 0; j < 7; j++) {
    uint32_t x0, x1, x2;
    asm volatile("ld.relaxed.gpu.global.v4.u32 {%0, %1, %2, %3}, [%4];"
                 : "=r"(x0), "=r"(x1), "=r"(x2), "=r"(tg[j]) : "l"(hp + 32 * j) : "memory");
    if (j < 4) kpv[3 * j] = x0; else vpv[3 * j - 10] = x0;
    if (j < 3) kpv[3 * j + 1] = x1; else vpv[3 * j - 9] = x1;
    if (j < 3) kpv[3 * j + 2] = x2; else if (j < 6) vpv[3 * j - 8] = x2;
  }
}

template <int ROT>
__device__ __forceinline__ void pack_qkv(const float* acc, uint32_t (&qlo)[10], uint32_t (&qhi)[10], uint32_t (&klo)[10],
                                         uint32_t (&khi)[10], uint32_t (&vlo)[10], uint32_t (&vhi)[10]) {
#pragma unroll
  for (int j = 0; j < 10; j++) {
    const int x = (j + ROT) % 10, tq = x < 8 ? x : 16 + x, tk = x < 8 ? 8 + x : 18 + x, tv = x < 8 ? 16 + x : 20 + x;
    khi[j] = pack2(acc[4 * tk + 2], acc[4 * tk + 3]);
    vhi[j] = movm(pack2(acc[4 * tv + 2], acc[4 * tv + 3]));
    qlo[j] = pack2(acc[4 * tq], acc[4 * tq + 1]);
    qhi[j] = pack2(acc[4 * tq + 2], acc[4 * tq + 3]);
    klo[j] = pack2(acc[4 * tk], acc[4 * tk + 1]);
    vlo[j] = pack2(acc[4 * tv], acc[4 * tv + 1]);
    asm volatile("" : "+r"(khi[j]), "+r"(qlo[j]), "+r"(qhi[j]), "+r"(klo[j]), "+r"(vlo[j]));
  }
}

template <int ROT> __device__ __forceinline__ void halo_send(const float* acc, uint4* ho, uint32_t tag) {
#pragma unroll
  for (int j = 0; j < 7; j++) {
    uint32_t x[3];
#pragma unroll
    for (int e = 0; e < 3; e++) {
      const int i = 3 * j + e, y = (i % 10 + ROT) % 10, tk = y < 8 ? 8 + y : 18 + y, tv = y < 8 ? 16 + y : 20 + y;
      x[e] = i < 10 ? pack2(acc[4 * tk + 2], acc[4 * tk + 3]) : i < 20 ? movm(pack2(acc[4 * tv + 2], acc[4 * tv + 3])) : 0u;
    }
    asm volatile("st.relaxed.gpu.global.v4.u32 [%0], {%1, %2, %3, %4};" ::"l"(ho + 32 * j), "r"(x[0]), "r"(x[1]), "r"(x[2]), "r"(tag) : "memory");
  }
}

__device__ __forceinline__ void attention(float* acc, uint32_t sb, int b, int par, int w, int lane, uint32_t tag, uint32_t zero) {
  const int g = lane >> 2, t = lane & 3;
  uint32_t klo[10], khi[10], vlo[10], vhi[10], qlo[10], qhi[10], kpv[10], vpv[10];
  if (HALO_FIRST && w == 3 && b < NCTA - 8) {
    uint4* ho = g_halo + (b * 2 + par) * 224 + lane;
    if (tail_first(b & 7)) halo_send<8>(acc, ho, tag);
    else halo_send<0>(acc, ho, tag);
    TSIF(par == 0, 76);
    pin<120>(acc);
  }
  if (tail_first(b & 7)) pack_qkv<8>(acc, qlo, qhi, klo, khi, vlo, vhi);
  else pack_qkv<0>(acc, qlo, qhi, klo, khi, vlo, vhi);
  const uint32_t xa = sb + OFF_KVX + (par * 3) * 2560 + lane * 16;
  if (w < 3) {
    sts128(xa + w * 2560, khi[0], khi[1], khi[2], khi[3]);
    sts128(xa + w * 2560 + 512, khi[4], khi[5], khi[6], khi[7]);
    sts128(xa + w * 2560 + 1024, khi[8], khi[9], vhi[0], vhi[1]);
    sts128(xa + w * 2560 + 1536, vhi[2], vhi[3], vhi[4], vhi[5]);
    sts128(xa + w * 2560 + 2048, vhi[6], vhi[7], vhi[8], vhi[9]);
  } else if (!HALO_FIRST && b < NCTA - 8) {
    uint4* ho = g_halo + (b * 2 + par) * 224 + lane;
#pragma unroll
    for (int j = 0; j < 7; j++) {
      const uint32_t x0 = j < 4 ? khi[3 * j] : vhi[3 * j - 10], x1 = j < 3 ? khi[3 * j + 1] : vhi[3 * j - 9];
      const uint32_t x2 = j < 3 ? khi[3 * j + 2] : j < 6 ? vhi[3 * j - 8] : 0u;
      asm volatile("st.relaxed.gpu.global.v4.u32 [%0], {%1, %2, %3, %4};" ::"l"(ho + 32 * j), "r"(x0), "r"(x1), "r"(x2), "r"(tag) : "memory");
    }
  }
  TSIF(par == 0 && w == 1, 64);
  TSIF(par == 0 && w == 3 && !HALO_FIRST, 76);
#pragma unroll
  for (int j = 0; j < 10; j++) vlo[j] = movm(vlo[j]);
  const bool far0 = 2 * t > g, far1 = 2 * t + 1 > g;
  const uint32_t mfar = (far0 ? 0x0000FFFFu : 0u) | (far1 ? 0xFFFF0000u : 0u);
  float slo[4][2], shi[4][2], lg[2][2];
  uint32_t phi[4], plo[4], qml[4], qmh[4];
#pragma unroll
  for (int h = 0; h < 4; h++) {
    const int f = h == 0 ? 0 : h == 1 ? 3 : h == 2 ? 5 : 8, hf = h < 2 ? 2 : 7;
    const bool mine = (h & 1) ? t >= 2 : t < 2;
    qml[h] = mine ? qlo[hf] : 0u;
    qmh[h] = mine ? qhi[hf] : 0u;
    float a[4] = {0.f, 0.f, 0.f, 0.f}, c[4] = {0.f, 0.f, 0.f, 0.f};
    mma16816(a, qlo[f], qhi[f], qlo[f + 1], qhi[f + 1], klo[f], klo[f + 1]);
    mma16816(c, qlo[f], qhi[f], qlo[f + 1], qhi[f + 1], khi[f], khi[f + 1]);
    mma1688(a, qml[h], qmh[h], klo[hf]);
    mma1688(c, qml[h], qmh[h], khi[hf]);
    slo[h][0] = a[0];
    slo[h][1] = a[1];
    shi[h][0] = lg[h & 1][0] = far0 ? a[2] : c[2];
    shi[h][1] = lg[h & 1][1] = far1 ? a[3] : c[3];
    if (!ATT_MERGE && (h & 1)) softmax_two(lg, phi[h - 1], phi[h]);
  }
  TSIF(par == 0 && w == 1, 65);
  if (ATT_GATE == 3 && lane == 0) mbar_arrive(sb + OFF_BAR + 8 * B_ATT2 + (phi[3] & zero));
  wg_sync(1 + par);
  TSIF(par == 0 && w == 1, 66);
  const bool nohist = (w == 0) && (b < 8);
  const uint4* hp = g_halo + ((b - 8) * 2 + par) * 224 + lane;
  uint32_t tg[7];
  if (w > 0) {
    const uint4 v0 = lds128(xa + (w - 1) * 2560), v1 = lds128(xa + (w - 1) * 2560 + 512), v2 = lds128(xa + (w - 1) * 2560 + 1024);
    const uint4 v3 = lds128(xa + (w - 1) * 2560 + 1536), v4 = lds128(xa + (w - 1) * 2560 + 2048);
    kpv[0] = v0.x; kpv[1] = v0.y; kpv[2] = v0.z; kpv[3] = v0.w; kpv[4] = v1.x; kpv[5] = v1.y; kpv[6] = v1.z; kpv[7] = v1.w;
    kpv[8] = v2.x; kpv[9] = v2.y; vpv[0] = v2.z; vpv[1] = v2.w; vpv[2] = v3.x; vpv[3] = v3.y; vpv[4] = v3.z; vpv[5] = v3.w;
    vpv[6] = v4.x; vpv[7] = v4.y; vpv[8] = v4.z; vpv[9] = v4.w;
  } else if (nohist) {
#pragma unroll
    for (int j = 0; j < 10; j++) kpv[j] = vpv[j] = 0u;
  } else {
    TSIF(par == 0, 77);
    halo_read(kpv, vpv, tg, hp);
  }
  if (w == 0 && !nohist) {
    int spins = 0;
    while (true) {
      bool ok = true;
#pragma unroll
      for (int j = 0; j < 7; j++) ok = ok && tg[j] == tag;
      if (__all_sync(0xffffffffu, ok) || ++spins > SPIN_LIMIT) break;
      halo_read(kpv, vpv, tg, hp);
    }
    TSIF(par == 0, 79);
  }
#pragma unroll
  for (int h = 0; h < 4; h++) {
    const int f = h == 0 ? 0 : h == 1 ? 3 : h == 2 ? 5 : 8, hf = h < 2 ? 2 : 7;
    float a[4] = {0.f, 0.f, 0.f, 0.f};
    mma16816(a, qlo[f], qhi[f], qlo[f + 1], qhi[f + 1], kpv[f], kpv[f + 1]);
    mma1688(a, qml[h], qmh[h], kpv[hf]);
    const float ninf = __int_as_float(0xff800000);
    lg[h & 1][0] = far0 ? (nohist ? ninf : a[0]) : slo[h][0];
    lg[h & 1][1] = far1 ? (nohist ? ninf : a[1]) : slo[h][1];
    if (h & 1) {
      softmax_two(lg, plo[h - 1], plo[h]);
      if (ATT_MERGE) {
        const float lh[2][2] = {{shi[h - 1][0], shi[h - 1][1]}, {shi[h][0], shi[h][1]}};
        softmax_two(lh, phi[h - 1], phi[h]);
      }
    }
  }
  TSIF(par == 0 && w <= 1, 67 + w);
  if (ATT_GATE == 2 && lane == 0) mbar_arrive(sb + OFF_BAR + 8 * B_ATT2 + (plo[3] & zero));
  uint32_t ov[20];
#pragma unroll
  for (int hp = 0; hp < 2; hp++) {
    const int hf = hp ? 7 : 2;
    float sh[4] = {0.f, 0.f, 0.f, 0.f}, i0 = 0.f, i1 = 0.f;
#pragma unroll
    for (int e = 0; e < 2; e++) {
      const int h = 2 * hp + e, f = h == 0 ? 0 : h == 1 ? 3 : h == 2 ? 5 : 8;
      const uint32_t a0 = plo[h] & mfar, a2 = plo[h] & ~mfar, a3 = phi[h] & mfar, c1 = phi[h] & ~mfar;
      float sum[4] = {0.f, 0.f, 0.f, 0.f};
      mma1688(sum, plo[h], phi[h], 0x3F803F80u);
      const float r0 = rcp(sum[0]), r1 = rcp(sum[2]);
#pragma unroll
      for (int j = f; j < f + 2; j++) {
        float o[4] = {0.f, 0.f, 0.f, 0.f};
        mma16816(o, a0, 0u, a2, a3, vpv[j], vlo[j]);
        mma1688(o, 0u, c1, vhi[j]);
        ov[2 * j] = pack2(o[0] * r0, o[1] * r0);
        ov[2 * j + 1] = pack2(o[2] * r1, o[3] * r1);
      }
      const bool mine = e ? g >= 4 : g < 4;
      mma16816(sh, a0, 0u, a2, a3, mine ? vpv[hf] : 0u, mine ? vlo[hf] : 0u);
      mma1688(sh, 0u, c1, mine ? vhi[hf] : 0u);
      if (e == 0 || t >= 2) {
        i0 = r0;
        i1 = r1;
      }
    }
    ov[2 * hf] = pack2(sh[0] * i0, sh[1] * i0);
    ov[2 * hf + 1] = pack2(sh[2] * i1, sh[3] * i1);
  }
  if (ATT_GATE == 4 && lane == 0) mbar_arrive(sb + OFF_BAR + 8 * B_ATT2 + (ov[19] & zero));
  TS(32 + 4 * par + w);
  mbar_wait(sb + OFF_BAR + 8 * B_P1, 0);
  const uint32_t oa = sb + OFF_OA + (lane >> 4) * 2048 + (32 * w + 2 * (lane & 15) + par) * 16;
#pragma unroll
  for (int j = 0; j < 5; j++) stsm4(oa + 4096 * j, ov + 4 * j);
  TSIF(par == 0 && w == 0, 120);
  fence_async_smem();
  TSIF(par == 0 && w == 0, 121);
  __syncwarp();
  if (lane == 0) mbar_arrive(sb + OFF_BAR + 8 * B_ATTN);
  TSM(w == 0 || w == 2, 122 + par + (w == 2 ? 3 : 0));
}

struct Maps {
  CUtensorMap x, wm, wt, k, v, y, wo, qm, qt, om, ot, u;
};

__device__ __forceinline__ void load_stage(uint32_t sb, int kb, int b, const Maps& m) {
  const uint32_t st = sb + (kb & 3) * STAGE_BYTES, bar = sb + OFF_BAR + 8 * (B_FULL1 + (kb & 3));
  const int r = b >> 3, hg = b & 7, slab = kb - KV_KB;
  const bool kv = slab >= 0 && slab < 5;
  const uint32_t kbar = sb + OFF_BAR + 8 * (B_KV + slab), dst = sb + OFF_KVS + slab * KVS_BYTES;
  mbar_expect_tx(bar, STAGE_BYTES);
  if (kv) mbar_expect_tx(kbar, KVS_BYTES);
  tma_3d(st, &m.x, 64 * kb, 64 * r, 0, bar);
  if (kv && KV_MIX) tma_3d(dst, &m.k, 0, 32 * (b >> 1) - 3, 2 * slab + (b & 1), kbar);
  tma_3d(st + ST_W, &m.wm, 80 * hg + (tail_first(hg) ? 16 : 0), 64 * kb, 0, bar);
  if (kv && KV_MIX) tma_3d(dst + KVS_V, &m.v, 0, 32 * (b >> 1), 2 * slab + (b & 1), kbar);
  tma_3d(st + ST_WT, &m.wt, 80 * hg + (tail_first(hg) ? 0 : 64), 64 * kb, 0, bar);
  if (kv && !KV_MIX) tma_3d(dst, &m.k, 0, 32 * (b >> 1) - 3, 2 * slab + (b & 1), kbar);
  if (kv && !KV_MIX) tma_3d(dst + KVS_V, &m.v, 0, 32 * (b >> 1), 2 * slab + (b & 1), kbar);
}

__global__ void __launch_bounds__(NTHR, 1) fused_kernel(const __grid_constant__ Maps m, const Params p) {
  extern __shared__ __align__(1024) uint8_t smem[];
  const uint32_t sb = (uint32_t)__cvta_generic_to_shared(smem);
  const uint32_t bars = sb + OFF_BAR;
  const int tid = threadIdx.x, lane = tid & 31;
  int b = blockIdx.x;
  if (BMAP == 1) b = (((b & 63) >> 3) * 2 + (b & 1)) * 8 + (((b < 64 ? 0x6521 : 0x7430) >> (4 * ((b >> 1) & 3))) & 7);
  if (BMAP == 2) b = ((b & 63) >> 2) * 8 + (((b < 64 ? 0x6521 : 0x7430) >> (4 * (b & 3))) & 7);
  if (BMAP == 3) b = (((b & 63) >> 3) * 2 + (b & 1)) * 8 + (((b < 64 ? 0x7430 : 0x6521) >> (4 * ((b >> 1) & 3))) & 7);
  if (BMAP == 4) b = (((b >> 4) * 2 + (b & 1)) * 8) + ((b >> 1) & 7);
  if (BMAP == 5) b = 127 - b;
  const int r = b >> 3, hg = b & 7;

  if (tid == T_ISSUE) {
    TSM(true, 0);
#pragma unroll
    for (int i = 0; i < 4; i++) mbar_init(bars + 8 * (B_FULL1 + i), 1);
#pragma unroll
    for (int i = 0; i < 3; i++) mbar_init(bars + 8 * (B_KV + i), 1);
    fence_async_smem();
#pragma unroll 1
    for (int kb = 0; kb <= PRE2; kb++) load_stage(sb, kb, b, m);
  } else if (tid >= T_PF && tid < T_PF + 12) {
    tm_prefetch(&m.x + (tid - T_PF));
  } else if (tid == T_INIT) {
#pragma unroll
    for (int i = 0; i < 4; i++) mbar_init(bars + 8 * (B_EMPTY1 + i), 8);
#pragma unroll
    for (int i = 0; i < 8; i++) mbar_init(bars + 8 * (B_FULL2 + i), 1);
#pragma unroll
    for (int i = 0; i < 4; i++) mbar_init(bars + 8 * (B_EMPTY2 + i), 8);
#pragma unroll
    for (int i = 0; i < 4; i++) mbar_init(bars + 8 * (B_U + i), 1);
    mbar_init(bars + 8 * B_HA, 4);
    mbar_init(bars + 8 * B_GATE, 4);
    mbar_init(bars + 8 * B_HB, 1);
    mbar_init(bars + 8 * B_KVD, 4);
    mbar_init(bars + 8 * B_QF, 1);
    mbar_init(bars + 8 * B_ATTN, 8);
    mbar_init(bars + 8 * B_ATT2, 8);
    mbar_init(bars + 8 * B_P1, 8);
    mbar_init(bars + 8 * B_C34, 1);
#pragma unroll
    for (int i = 0; i < 5; i++) mbar_init(bars + 8 * (B_YST + i), 4);
#pragma unroll
    for (int i = 0; i < 5; i++) mbar_init(bars + 8 * (B_US + i), 4);
    mbar_init(bars + 8 * B_YSIG, 1);
    mbar_init(bars + 8 * B_YFULL, 1);
    mbar_init(bars + 8 * B_EPOCH, 1);
    mbar_init(bars + 8 * B_PREP, 4);
    mbar_init(bars + 8 * B_USIG, 1);
    mbar_init(bars + 8 * B_WST, 1);
#pragma unroll
    for (int i = 3; i < 5; i++) mbar_init(bars + 8 * (B_KV + i), 1);
    mbar_init(bars + 8 * B_E3, 8);
    mbar_init(bars + 8 * B_LAST, 1);
    mbar_init(bars + 8 * B_OSIG, 1);
    mbar_init(bars + 8 * B_WOP, 1);
    fence_async_smem();
  }
  const int warp = __shfl_sync(0xffffffffu, tid >> 5, 0), wg = warp >> 2, w = warp & 3;
  __syncthreads();

  if (wg == 3) {
    asm volatile("setmaxnreg.dec.sync.aligned.u32 56;");
    if (w == 0) {
      if (lane == 0) {
#pragma unroll 1
        for (int kb = 1 + PRE2; kb < 10; kb++) {
          if (kb >= 4) mbar_wait(bars + 8 * (kb == 7 ? B_E3 : B_EMPTY1 + (kb & 3)), (kb >> 3) & 1);
          TSIF(kb >= 4, 44 + kb);
          load_stage(sb, kb, b, m);
          TSIF(kb == 3, 60);
          if (kb == TRIG_KB) mbar_arrive(bars + 8 * B_LAST);
        }
        mbar_wait(bars + 8 * B_WOP, 0);
        mbar_wait(bars + 8 * WL_TRIG, 0);
        mbar_wait(bars + 8 * B_EPOCH, 0);
        flag_wait(g_cnt + C_W + 32 * hg, (lds32(sb + OFF_EPOCH) + 1) * 16);
        TS(30);
#pragma unroll 1
        for (int j = 0; j < 8; j++) {
          if (j >= 6) mbar_wait(bars + 8 * (B_EMPTY2 + j - 6), 0);
          if (j == 4) mbar_wait(bars + 8 * B_ATTN, 0);
          TSIF(j >= 6, 100 + j);
          if (RF_GATE && j == 6) mbar_wait(bars + 8 * B_YSIG, 0);
          mbar_expect_tx(bars + 8 * (B_FULL2 + j), j == 0 ? WO_BYTES : j == 5 ? O_BYTES + WO_BYTES + 512 : O_BYTES + WO_BYTES);
          bulk_load(sb + off_w(j), g_WO + (hg * 8 + step_src(hg, j)) * 800, WO_BYTES, bars + 8 * (B_FULL2 + j));
        }
        mbar_wait(bars + 8 * (B_EMPTY2 + 3), 0);
        mbar_expect_tx(bars + 8 * B_QF, O_BYTES);
        tma_2d(sb + OFF_QS, &m.qm, 80 * hg, 128 * r, bars + 8 * B_QF);
        tma_2d(sb + OFF_QT, &m.qt, 80 * hg + 64, 128 * r, bars + 8 * B_QF);
      }
    } else if (w == 1) {
      unsigned epoch = 0;
      if (lane == 0) {
        epoch = atomicAdd(g_cnt + C_LAUNCH, 1u) / NCTA;
        asm volatile("st.shared.u32 [%0], %1;" ::"r"(sb + OFF_EPOCH), "r"(epoch) : "memory");
        mbar_arrive(bars + 8 * B_EPOCH);
        mbar_wait(bars + 8 * B_KVD, 0);
        mbar_expect_tx(bars + 8 * B_HB, 5 * 4096);
#pragma unroll 1
        for (int c = 0; c < 5; c++) {
          if (c == 3) mbar_wait(bars + 8 * B_S3, 0);
          bulk_load(sb + off_ch(c) + U_BYTES, p.ssm_k + (5 * b + c) * SEQ, 4096, bars + 8 * B_HB);
        }
#pragma unroll
        for (int c = 0; c < 4; c++) mbar_expect_tx(bars + 8 * (B_U + c), c < 3 ? U_BYTES : 2 * U_BYTES);
        const uint4* usrc = g_U + 5 * b * U_PITCH;
        mbar_wait(bars + 8 * B_USIG, 0);
        flag_wait(g_cnt + C_PREP + 32 * (b & 15), (epoch + 1) * NCTA);
        TS(23);
#pragma unroll
        for (int c = 0; c < 5; c++) {
          if (c == 3 && U_TRIM) mbar_wait(bars + 8 * (B_U + 2), 0);
          bulk_load(sb + off_ch(c), usrc + c * U_PITCH, U_BYTES, bars + 8 * (B_U + (c < 3 ? c : 3)));
          TSIF(c == 0 || c == 4, 116 + (c >> 2));
        }
      }
      epoch = __shfl_sync(0xffffffffu, epoch, 0);
      if (lane < 8) {
        const int src = (b & ~7) | step_src(hg, lane);
        mbar_wait(bars + 8 * OP_TRIG, 0);
        TS(20);
        bool seen = false;
#pragma unroll 1
        for (int spins = 0; spins < SPIN_LIMIT; spins++) {
          const bool now = !seen && (int)(flag_read(g_cnt + C_O + 32 * src) - (epoch + 1)) >= 0;
          if (now && lane >= 1 && lane < 4) bulk_load(sb + off_o(lane), g_O + src * 1280, O_BYTES, bars + 8 * (B_FULL2 + lane));
          seen = seen || now;
          if (__all_sync(0xff, seen)) break;
        }
        TS(21);
        if (lane == 5) bulk_load(sb + OFF_GATE, g_gate + 128 * r, 512, bars + 8 * (B_FULL2 + 5));
#pragma unroll 1
        for (int j = 4; j < 8; j++) {
          if (lane == j) {
            mbar_wait(bars + 8 * (j < 6 ? B_C34 : B_EMPTY2 + j - 6), 0);
            if (RF_GATE && j == 6) mbar_wait(bars + 8 * B_YSIG, 0);
            bulk_load(sb + off_o(j), g_O + src * 1280, O_BYTES, bars + 8 * (B_FULL2 + j));
          }
          __syncwarp(0xff);
        }
        TS(22);
      }
    } else if (w == 2) {
      mbar_wait(bars + 8 * B_PREP, 0);
      flag_signal(g_cnt + C_PREP, 16, lane);
      TS(25);
      if (lane == 0) mbar_arrive(bars + 8 * B_USIG);
      mbar_wait(bars + 8 * B_GATE, 0);
      if (((NOMB & 1) || O_RB) && lane == 0) asm volatile("fence.release.gpu;" ::: "memory");
      mbar_wait(bars + 8 * B_ATTN, 0);
      if (lane == 0) {
        if (O_DEFER) mbar_wait(bars + 8 * (B_U + 3), 0);
        asm volatile("cp.async.bulk.global.shared::cta.bulk_group [%0], [%1], 20480;\ncp.async.bulk.commit_group;"
                     ::"l"(g_O + b * 1280), "r"(sb + OFF_OA) : "memory");
        if (O_RB) asm volatile("cp.async.bulk.wait_group.read 0;" ::: "memory");
        else asm volatile("cp.async.bulk.wait_group 0;\nfence.proxy.async.global;" ::: "memory");
      }
      TS(74);
      if (O_RB) {
        __syncwarp();
        unsigned v[5];
#pragma unroll
        for (int c = 0; c < 5; c++) v[c] = flag_read(reinterpret_cast<const unsigned*>(g_O + b * 1280 + 256 * c + 8 * lane + 7));
        const unsigned dep = __reduce_or_sync(0xffffffffu, (v[0] ^ v[1] ^ v[2] ^ v[3] ^ v[4]) & p.zero);
        if (lane == 0) flag_bump(g_cnt + C_O + 32 * b + dep);
      } else if (!(NOMB & 1)) flag_signal(g_cnt + C_O + 32 * b, 1, lane);
      else if (lane == 0) flag_bump(g_cnt + C_O + 32 * b);
      TS(26);
      if (lane == 0) mbar_arrive(bars + 8 * B_OSIG);

    } else {
      if (lane == 0) {
        uint4* dst = g_WO + (hg * 8 + (r >> 1)) * 800 + (r & 1) * 80;
        mbar_wait(bars + 8 * B_P1, 0);
        mbar_wait(bars + 8 * WB_TRIG, 0);
        mbar_expect_tx(bars + 8 * B_WST, WO_BYTES / 2);
        tma_3d(sb + OFF_WS, &m.wo, 0, 40 * r, 5 * hg, bars + 8 * B_WST);
        mbar_wait(bars + 8 * B_WST, 0);
        mbar_wait(bars + 8 * WO_TRIG, 0);
#pragma unroll 1
        for (int n = 0; n < 5; n++)
          asm volatile("cp.async.bulk.global.shared::cta.bulk_group [%0], [%1], 1280;" ::"l"(dst + 160 * n), "r"(sb + OFF_WS + 1280 * n) : "memory");
        asm volatile("cp.async.bulk.commit_group;\ncp.async.bulk.wait_group 0;\nfence.proxy.async.global;" ::: "memory");
        if (!(NOMB & 4)) asm volatile("fence.release.gpu;" ::: "memory");
        flag_bump(g_cnt + C_W + 32 * hg);
        mbar_arrive(bars + 8 * B_WOP);
        TS(71);
#pragma unroll 1
        for (int c = 0; c < 5; c++) {
          mbar_wait(bars + 8 * (B_YST + c), 0);
          asm volatile("cp.async.bulk.global.shared::cta.bulk_group [%0], [%1], 4096;\ncp.async.bulk.commit_group;"
                       ::"l"(g_Y + (5 * b + c) * Y_PITCH), "r"(sb + off_ch(c)) : "memory");
          if (c == 2) {
            asm volatile("cp.async.bulk.wait_group.read 0;" ::: "memory");
            mbar_arrive(bars + 8 * B_C34);
          }
        }
        if (Y_RB) asm volatile("cp.async.bulk.wait_group.read 0;" ::: "memory");
        else asm volatile("cp.async.bulk.wait_group 0;\nfence.proxy.async.global;" ::: "memory");
        TS(75);
      }
      unsigned dep = 0;
      if (Y_RB) {
        __syncwarp();
        unsigned v[5];
#pragma unroll
        for (int c = 0; c < 5; c++) v[c] = flag_read(reinterpret_cast<const unsigned*>(g_Y + (5 * b + c) * Y_PITCH + 8 * lane + 7));
        dep = __reduce_or_sync(0xffffffffu, (v[0] ^ v[1] ^ v[2] ^ v[3] ^ v[4]) & p.zero);
      }
      if (lane == 0) {
        if (!Y_RB && !(NOMB & 2)) asm volatile("fence.release.gpu;" ::: "memory");
        flag_bump(g_cnt + C_Y + 32 * (b >> 4) + dep);
        TS(27);
        mbar_arrive(bars + 8 * B_YSIG);
        mbar_expect_tx(bars + 8 * B_YFULL, 20480);
        flag_wait(g_cnt + C_Y + 32 * hg, (lds32(sb + OFF_EPOCH) + 1) * 16);
        TS(24);
        tma_2d(sb + OFF_YT, &m.y, 128 * r, 80 * hg, bars + 8 * B_YFULL);
        tma_2d(sb + OFF_YT + 10240, &m.y, 128 * r + 64, 80 * hg, bars + 8 * B_YFULL);
      }
    }
  } else {
    asm volatile("setmaxnreg.inc.sync.aligned.u32 152;");
    if (wg < 2) {
      float acc[120];
#pragma unroll
      for (int i = 0; i < 120; i++) acc[i] = 0.f;
      const uint32_t da = desc_lo(sb + wg * 8192, 16), db = desc_lo(sb + ST_W, 8192), dc = desc_lo(sb + ST_WT, 2048);
      if (PW1) pin<120>(acc);
      if (PW1 == 2) mbar_wait(bars + 8 * B_FULL1, 0);
#pragma unroll 1
      for (int kb = 0; kb < 10; kb++) {
        mbar_wait(bars + 8 * (B_FULL1 + (kb & 3)), (kb >> 2) & 1);
        const uint32_t so = (kb & 3) * (STAGE_BYTES >> 4);
        wg_fence();
#pragma unroll
        for (int k = 0; k < 4; k++) {
          WgSST<192>::mma<HI_SW128, HI_SW128>(acc, da + so + 2 * k, db + so + 128 * k, 1);
          WgSST<48>::mma<HI_SW128, HI_SW32>(acc + 96, da + so + 2 * k, dc + so + 32 * k, 1);
        }
        wg_commit();
        wg_wait<1>();
        if (kb > 0 && lane == 0) mbar_arrive(bars + 8 * (kb == 4 ? B_E3 : B_EMPTY1 + ((kb - 1) & 3)));
      }
      mbar_wait(bars + 8 * B_EPOCH, 0);
      const uint32_t tag = lds32(sb + OFF_EPOCH) + 1;
      mbar_wait(bars + 8 * B_S3, 0);
      wg_wait<0>();
      pin<120>(acc);
      if (lane == 0) mbar_arrive(bars + 8 * B_P1);
      TSM(w == 0, 3 + wg);
      attention(acc, sb, b, wg, w, lane, tag, p.zero);
    } else {
      const int tw = tid & 127, chl = 64 * (b & 1) + 8 * w + (lane >> 2);
      uint4* up = g_U + chl * U_PITCH + ((4 * (b >> 1) + (lane & 3)) ^ ((b >> 2) & 1));
      uint2 sw[10];
      uint32_t dv = 0;
      if (lane < 5) dv = __ldg(reinterpret_cast<const unsigned short*>(p.ssm_D) + 5 * b + lane);
#pragma unroll
      for (int i = 0; i < 10; i++) sw[i] = ldg64(reinterpret_cast<const uint2*>(p.shift_k) + chl + 128 * (i >> 1) + 32 * (i & 1));
      uint32_t tab[12];
      uint32_t tt[2];
      fft_tables(tab, tw);
      fft_twiddles(tt, tw);
      uint4 res[10];
#pragma unroll
      for (int i = 0; i < 10; i++) res[i] = make_uint4(0, 0, 0, 0);
#pragma unroll 1
      for (int slab = 0; slab < 5; slab++) {
#pragma unroll
        for (int i = 0; i < 8; i++) res[i] = res[i + 2];
        prep_slab(res + 8, sw, sb, slab, w, lane);
        TSIF(w == 0, 99 + 4 * slab);
#pragma unroll
        for (int i = 0; i < 8; i++) sw[i] = sw[i + 2];
      }
      TSIF(w == 0, 28);
      __syncwarp();
      if (lane == 0) mbar_arrive(bars + 8 * B_KVD + ((res[8].x ^ res[9].x) & p.zero));
      mbar_wait(bars + 8 * B_KVD, 0);
      fft_tables_store(tab, sb, tw);
      uint4 gw[5], gx[10];
      if (G_POS == 2) gate_load(gw, gx, p, 16 * b + 4 * w, lane);
      mbar_wait(bars + 8 * B_LAST, 0);
#pragma unroll
      for (int i = 0; i < 10; i++) up[(128 * (i >> 1) + 32 * (i & 1)) * U_PITCH] = res[i];
      __syncwarp();
      if (lane == 0) mbar_arrive(bars + 8 * B_PREP);
      TSIF(w == 0 && !U_TMA, 5);
      mbar_wait(bars + 8 * (G_AFTER ? B_USIG : B_LAST), 0);
      if (G_POS == 0) gate_load(gw, gx, p, 16 * b + 4 * w, lane);
      gate_finish(gw, gx, 16 * b + 4 * w, lane);
      __syncwarp();
      if (lane == 0) mbar_arrive(bars + 8 * B_GATE);
      TSIF(w == 0, 72);
      mbar_wait(bars + 8 * B_HB, 0);
      TSIF(w == 0, 2);
      const uint32_t ha = sb + U_BYTES + ((tw >> 3) * 16 + 8 + (tw & 7)) * 16;
      uint4 hv[5];
#pragma unroll
      for (int c = 0; c < 5; c++) hv[c] = lds128(ha + off_ch(c));
      __syncwarp();
#pragma unroll
      for (int c = 0; c < 5; c++) sts128((ha ^ 16) + off_ch(c), hv[c].x, hv[c].y, hv[c].z, hv[c].w);
      asm volatile("st.shared.v2.u32 [%0], {%1, %2};" ::"r"(sb + OFF_TT + 8 * tw), "r"(tt[0]), "r"(tt[1]) : "memory");
      if (tw < 5) asm volatile("st.shared.f32 [%0], %1;" ::"r"(sb + OFF_D + 4 * tw), "f"(bf_lo(dv) * 0.125f) : "memory");
      fence_async_smem();
      __syncwarp();
      if (lane == 0) mbar_arrive(bars + 8 * B_HA);
      TSIF(w == 0, 6);
    }

    FftConst fc;
    TSM(w == 0 && wg == 0, 104);
    mbar_wait(bars + 8 * B_HA, 0);
    fft_matrices(fc, sb, w, lane);
    TSM(w == 0 && wg == 0, 105);
    TSM(w == 0 && wg == 2, 124);
#pragma unroll 1
    for (uint32_t tasks = wg == 0 ? TASK0 : wg == 1 ? TASK1 : TASK2; tasks; tasks >>= 4) {
      const int c = (tasks & 7) - 1;
      conv_channel(fc, sb, c, wg, w, lane);
      if (lane == 0) mbar_arrive(bars + 8 * (B_YST + c));
      TSM(w == 0, 10 + c);
    }

    if (wg < 2) {
      const int g = lane >> 2;
      float acc[40];
#pragma unroll
      for (int i = 0; i < 40; i++) acc[i] = 0.f;
      const uint32_t da = desc_lo(sb + wg * 1024, 2048), db = desc_lo(sb, 2560);
      if (!WO_FAST) mbar_wait(bars + 8 * B_ATTN, 0);
      mbar_wait(bars + 8 * (B_YST + 3), 0);
      mbar_wait(bars + 8 * (B_YST + 4), 0);
      if (PW2 && !WO_FAST) mbar_wait(bars + 8 * B_FULL2, 0);
      TSM(w == 0, 15 + wg);
#pragma unroll 1
      for (int j = 0; j < 8; j++) {
        mbar_wait(bars + 8 * (B_FULL2 + j), 0);
        const uint32_t oa = da + (off_o(j) >> 4), ob = db + (off_w(j) >> 4);
        wg_fence();
#pragma unroll
        for (int k = 0; k < 5; k++) WgSST<80>::mma<HI_NONE, HI_SW32>(acc, oa + 256 * k, ob + 32 * k, 1);
        wg_commit();
        wg_wait<1>();
        if (j >= 1 && j <= 4 && lane == 0) mbar_arrive(bars + 8 * (B_EMPTY2 + j - 1));
      }
      TSIF(w == 0 && wg == 0, 113);
      const int tr = 64 * wg + 16 * w + (lane & 15);
      const uint32_t fm = sb + OFF_QS + tr * 128, fx = (lane >> 4) ^ (tr & 7);
      const uint32_t ft = sb + OFF_QT + tr * 32 + (((lane >> 4) ^ (tr >> 2)) & 1) * 16;
      const float g0 = __uint_as_float(lds32(sb + OFF_GATE + (64 * wg + 16 * w + g) * 4));
      const float g1 = __uint_as_float(lds32(sb + OFF_GATE + (64 * wg + 16 * w + 8 + g) * 4));
      const uint32_t ga = pack2(g0, g0), gb = pack2(g1, g1);
      const uint32_t na = pack2(1.f - g0, 1.f - g0), nb = pack2(1.f - g1, 1.f - g1);

      uint32_t qf[20];
      mbar_wait(bars + 8 * B_QF, 0);
#pragma unroll
      for (int j = 0; j < 5; j++) ldsm4(qf + 4 * j, j < 4 ? fm + ((fx ^ (2 * j)) << 4) : ft);
      if (FUSE_MIX) {
#pragma unroll
        for (int i = 0; i < 20; i++) {
          qf[i] = bmul((i & 1) ? gb : ga, qf[i]);
          asm volatile("" : "+r"(qf[i]));
        }
      }
      wg_wait<0>();
      pin<40>(acc);
      TSM(w == 0, 17 + wg);
      uint32_t pb[20];
#pragma unroll
      for (int j = 0; j < 10; j++) {
        pb[2 * j] = bmul(na, pack2(acc[4 * j], acc[4 * j + 1]));
        pb[2 * j + 1] = bmul(nb, pack2(acc[4 * j + 2], acc[4 * j + 3]));
        asm volatile("" : "+r"(pb[2 * j]), "+r"(pb[2 * j + 1]));
      }
      const uint32_t ya = sb + OFF_YT + wg * 10240 + ((lane >> 4) * 8 + (lane & 7)) * 128 +
                          (((2 * w + (((lane >> 3) & 1) ^ wg)) ^ (lane & 7)) << 4);
      mbar_wait(bars + 8 * B_YFULL, 0);
      TSM(w == 0 && wg == 0, 19);
#pragma unroll
      for (int j = 0; j < 5; j++) {
        uint32_t y[4];
        ldsm4t(y, ya + 2048 * j);
#pragma unroll
        for (int i = 0; i < 4; i++)
          qf[4 * j + i] = FUSE_MIX ? bfma(qf[4 * j + i], y[i], pb[4 * j + i]) : badd(bmul((i & 1) ? gb : ga, bmul(qf[4 * j + i], y[i])), pb[4 * j + i]);
      }
#pragma unroll
      for (int j = 0; j < 5; j++) stsm4(j < 4 ? fm + ((fx ^ (2 * j)) << 4) : ft, qf + 4 * j);
      fence_async_smem();
      __syncwarp();
      if (lane == 0) {
        const int row = 64 * wg + 16 * w;
        asm volatile("cp.async.bulk.tensor.2d.global.shared::cta.bulk_group [%0, {%2, %3}], [%1];"
                     ::"l"(&m.om), "r"(sb + OFF_QS + row * 128), "r"(80 * hg), "r"(128 * r + row) : "memory");
        asm volatile("cp.async.bulk.tensor.2d.global.shared::cta.bulk_group [%0, {%2, %3}], [%1];"
                     ::"l"(&m.ot), "r"(sb + OFF_QT + row * 32), "r"(80 * hg + 64), "r"(128 * r + row) : "memory");
        asm volatile("cp.async.bulk.commit_group;\ncp.async.bulk.wait_group.read 0;" ::: "memory");
      }
      TSM(true, 40 + 4 * wg + w);
      if (ENDBAR) asm volatile("bar.sync 15, 256;" ::: "memory");
    }
  }
}

typedef CUresult (*EncodeFn)(CUtensorMap*, CUtensorMapDataType, cuuint32_t, void*, const cuuint64_t*, const cuuint64_t*,
                             const cuuint32_t*, const cuuint32_t*, CUtensorMapInterleave, CUtensorMapSwizzle,
                             CUtensorMapL2promotion, CUtensorMapFloatOOBfill);

void encode(EncodeFn fn, CUtensorMap* tm, const void* base, int rank, const cuuint64_t* dims, const cuuint64_t* strides,
            const cuuint32_t* box, CUtensorMapSwizzle swz) {
  const cuuint32_t ones[3] = {1, 1, 1};
  fn(tm, CU_TENSOR_MAP_DATA_TYPE_BFLOAT16, rank, const_cast<void*>(base), dims, strides, box, ones,
     CU_TENSOR_MAP_INTERLEAVE_NONE, swz, CU_TENSOR_MAP_L2_PROMOTION_L2_128B, CU_TENSOR_MAP_FLOAT_OOB_FILL_NONE);
}

}

extern "C" void kernel_launch(void* const* d_in, const int* in_sizes, int n_in, void* d_out, int out_size) {
  (void)in_sizes; (void)n_in; (void)out_size;
  Params p;
  p.q = (const __nv_bfloat16*)d_in[0];
  p.k = (const __nv_bfloat16*)d_in[1];
  p.v = (const __nv_bfloat16*)d_in[2];
  p.shift_k = (const __nv_bfloat16*)d_in[3];
  p.ssm_k = (const __nv_bfloat16*)d_in[4];
  p.ssm_D = (const __nv_bfloat16*)d_in[5];
  p.wqkv = (const __nv_bfloat16*)d_in[7];
  p.wo = (const __nv_bfloat16*)d_in[8];
  p.gate_w = (const __nv_bfloat16*)d_in[9];
  p.out = (__nv_bfloat16*)d_out;
  p.zero = 0;

  static EncodeFn fn = nullptr;
  static void *yaddr = nullptr, *uaddr = nullptr;
  if (!fn) {
    cudaDriverEntryPointQueryResult qr;
    void* f = nullptr;
    cudaGetDriverEntryPoint("cuTensorMapEncodeTiled", &f, cudaEnableDefault, &qr);
    fn = (EncodeFn)f;
    cudaGetSymbolAddress(&yaddr, g_Y);
    cudaGetSymbolAddress(&uaddr, g_U);
    cudaFuncSetAttribute(fused_kernel, cudaFuncAttributeMaxDynamicSharedMemorySize, SMEM_BYTES);
  }
  Maps m;
  {
    const cuuint64_t dims[3] = {640, 1024, 2}, st[2] = {2560, 1280};
    const cuuint32_t box[3] = {64, 64, 2};
    encode(fn, &m.x, p.q, 3, dims, st, box, CU_TENSOR_MAP_SWIZZLE_128B);
  }
  {
    const cuuint64_t dims[3] = {640, 640, 3}, st[2] = {3840, 1280};
    const cuuint32_t box[3] = {64, 64, 3}, boxt[3] = {16, 64, 3};
    encode(fn, &m.wm, p.wqkv, 3, dims, st, box, CU_TENSOR_MAP_SWIZZLE_128B);
    encode(fn, &m.wt, p.wqkv, 3, dims, st, boxt, CU_TENSOR_MAP_SWIZZLE_32B);
  }
  {
    const cuuint64_t dims[3] = {64, 2048, 10}, st[2] = {1280, 128};
    const cuuint32_t boxk[3] = {64, 35, 1}, boxv[3] = {64, 32, 1};
    encode(fn, &m.k, p.k, 3, dims, st, boxk, CU_TENSOR_MAP_SWIZZLE_128B);
    encode(fn, &m.v, p.v, 3, dims, st, boxv, CU_TENSOR_MAP_SWIZZLE_128B);
  }
  {
    const cuuint64_t dims[3] = {16, 640, 40}, st[2] = {1280, 32};
    const cuuint32_t box[3] = {16, 40, 5};
    encode(fn, &m.wo, p.wo, 3, dims, st, box, CU_TENSOR_MAP_SWIZZLE_32B);
  }
  {
    const cuuint64_t dims[2] = {2048, 640}, st[1] = {Y_PITCH * 16};
    const cuuint32_t box[2] = {64, 80};
    encode(fn, &m.y, yaddr, 2, dims, st, box, CU_TENSOR_MAP_SWIZZLE_128B);
    const cuuint64_t stu[1] = {U_PITCH * 16};
    const cuuint32_t boxu[2] = {32, 64};
    encode(fn, &m.u, uaddr, 2, dims, stu, boxu, CU_TENSOR_MAP_SWIZZLE_NONE);
  }
  {
    const cuuint64_t dims[2] = {640, 2048}, st[1] = {1280};
    const cuuint32_t bqm[2] = {64, 128}, bqt[2] = {16, 128}, bom[2] = {64, 16}, bot[2] = {16, 16};
    encode(fn, &m.qm, p.q, 2, dims, st, bqm, CU_TENSOR_MAP_SWIZZLE_128B);
    encode(fn, &m.qt, p.q, 2, dims, st, bqt, CU_TENSOR_MAP_SWIZZLE_32B);
    encode(fn, &m.om, p.out, 2, dims, st, bom, CU_TENSOR_MAP_SWIZZLE_128B);
    encode(fn, &m.ot, p.out, 2, dims, st, bot, CU_TENSOR_MAP_SWIZZLE_32B);
  }
  fused_kernel<<<NCTA, NTHR, SMEM_BYTES>>>(m, p);
}
```

```cpp
#include <cuda.h>
#include <cuda_bf16.h>
#include <cuda_runtime.h>
#include <stdint.h>

namespace {

constexpr int SEQ = 2048, DIM = 640, NCTA = 128, NTHR = 512;

#define TRIG_KB 9
#define KV_KB 2
#define DEV_EXIT 0
#define ATT_GATE 0
#define G_AFTER 0
#define FENCE_LO 0
#define FENCE_HI 0
#define PW1 2
#define PW2 1
#define ENDBAR 0
#define PAD_KB 0
#define Y_ALIAS 1
#define NOMB 0
#define SRC_ROT 0
#define WAIT_NS 0
#define WB_TRIG B_USIG
#define G_POS 0
#define TAILF 1
#define T_ISSUE 384
#define T_PF 416
#define T_INIT 448
#define ATT_MERGE 0
#define BMAP 1
#define PRE2 1
#define KV_MIX 0
#define O_DEFER 0
#define TASK0 0x52
#define TASK1 0x3
#define TASK2 0x41
#define HALO_FIRST 1
#define PREV_EARLY 0
#define Y_RB 0
#define O_RB 0
#define O_EAGER 1
#define OP_TRIG B_OSIG
#define FUSE_MIX 1
#define Q_EARLY 1
#define WO_FAST 0
#define U_TRIM 1
#define ACQ 0
#define U_TMA 0
#define U_GATE 0
#define RF_GATE 0
#define WO_TRIG B_WST
#define WL_TRIG B_WOP
#define WO_GATE 1

constexpr uint32_t STAGE_BYTES = 47104, ST_W = 16384, ST_WT = 40960;
constexpr uint32_t O_BYTES = 20480, WO_BYTES = 12800;
constexpr uint32_t OFF_OA = 0;
constexpr uint32_t OFF_QS = 3 * O_BYTES, OFF_QT = OFF_QS + 16384;
constexpr uint32_t OFF_WC = 81920;
constexpr uint32_t OFF_WA = 94720;
constexpr uint32_t OFF_GATE = 145920;
constexpr uint32_t OFF_TT = 146432;
constexpr uint32_t OFF_KVX = 148480;
constexpr uint32_t OFF_CH3 = 163840;
constexpr uint32_t CH_BYTES = 12288, U_BYTES = 4096;
constexpr uint32_t OFF_FT = 225280, OFF_GT = 229376;
constexpr uint32_t OFF_CH0 = 188416;
constexpr uint32_t OFF_KVS = OFF_CH0, KVS_V = 4480, KVS_BYTES = 8576;
constexpr uint32_t OFF_WS = OFF_WA;
__device__ __forceinline__ uint32_t off_us(int s) { return OFF_CH0 + 4096 * ((0x65320 >> (4 * s)) & 7); }
constexpr uint32_t OFF_YT = 163840;
constexpr uint32_t OFF_BAR = 231936;
constexpr uint32_t SMEM_BYTES = OFF_BAR + 512;

enum : uint32_t {
  B_FULL1 = 0, B_EMPTY1 = 4, B_S3 = 7, B_FULL2 = 52, B_EMPTY2 = 13, B_U = 8, B_GATE = 12, B_HA = 19, B_HB = 20,
  B_ATTN = 21, B_C34 = 22, B_CONV = 23, B_YFULL = 24, B_EPOCH = 25, B_PREP = 26, B_P1 = 27, B_LAST = 28,
  B_E3 = 29, B_OSIG = 30, B_WOP = 31, B_USIG = 32, B_WST = 33, B_KV = 34, B_KVD = 39, B_QF = 17, B_ATT2 = 18, B_YST = 40,
  B_US = 45, B_YSIG = 50
};
constexpr uint32_t OFF_EPOCH = OFF_BAR + 8 * 51, OFF_D = OFF_BAR + 8 * 60;
__device__ __forceinline__ uint32_t off_o(int j) { return j < 4 ? OFF_OA + j * O_BYTES : j < 6 ? OFF_CH0 + (j - 4) * O_BYTES : OFF_OA + (j - 6) * O_BYTES; }
__device__ __forceinline__ uint32_t off_w(int j) { return j < 4 ? OFF_WA + j * WO_BYTES : j == 4 ? OFF_KVX : j == 5 ? OFF_WC : OFF_WA + (j - 6) * WO_BYTES; }
__device__ __forceinline__ int step_src(int hg, int j) {
  if (SRC_ROT == 2) {
    const int pos = (0x37621540 >> (4 * hg)) & 7;
    return j == 0 ? hg : (0x65217430 >> (4 * (j <= pos ? j - 1 : j))) & 7;
  }
  return SRC_ROT ? (hg + j) & 7 : j == 0 ? hg : j <= hg ? j - 1 : j;
}
__device__ __forceinline__ bool tail_first(int hg) { return TAILF && (hg & 3) == 3; }
__device__ __forceinline__ uint32_t off_ch(int c) { return (c < 3 ? OFF_CH0 : OFF_CH3 - 3 * CH_BYTES) + c * CH_BYTES; }

#define U_PITCH 264
__device__ __align__(1024) uint4 g_U[DIM * U_PITCH];
__device__ uint4 g_O[NCTA * 1280];
#define g_Y g_U
constexpr int Y_PITCH = U_PITCH;
__device__ uint4 g_WO[64 * 800];
__device__ uint4 g_halo[NCTA * 2 * 7 * 32];
__device__ float g_gate[SEQ + PAD_KB * 256];
__device__ unsigned g_cnt[32 * (1 + 2 * 16 + 8 + NCTA)];
constexpr int C_LAUNCH = 0, C_PREP = 32, C_Y = 32 * 17, C_W = 32 * 33, C_O = 32 * 41;

#define TSM(cond, slot) do { } while (0)
#define TSIF(cond, slot) do { if (__LINE__ >= FENCE_LO && __LINE__ < FENCE_HI) sched_fence(); } while (0)
__device__ __forceinline__ void sched_fence() {
  asm volatile("{\n.reg .pred p;\n.reg .u32 c;\nmov.u32 c, %%clock;\nsetp.eq.u32 p, c, 0;\n@p st.shared.u32 [%0], c;\n}"
               ::"r"(1024 + OFF_EPOCH + 4) : "memory");
}
#define TS(slot) TSIF(true, slot)

struct Params {
  const __nv_bfloat16 *q, *k, *v, *shift_k, *ssm_k, *ssm_D, *wqkv, *wo, *gate_w;
  __nv_bfloat16* out;
  uint32_t zero;
};

#define POLL_NS 0
constexpr int SPIN_LIMIT = 1 << 17;

__device__ __forceinline__ void mbar_init(uint32_t bar, uint32_t count) {
  asm volatile("mbarrier.init.shared::cta.b64 [%0], %1;" ::"r"(bar), "r"(count) : "memory");
}
__device__ __forceinline__ void mbar_expect_tx(uint32_t bar, uint32_t bytes) {
  asm volatile("mbarrier.arrive.expect_tx.shared::cta.b64 _, [%0], %1;" ::"r"(bar), "r"(bytes) : "memory");
}
__device__ __forceinline__ void mbar_arrive(uint32_t bar) {
  asm volatile("mbarrier.arrive.shared::cta.b64 _, [%0];" ::"r"(bar) : "memory");
}
__device__ __forceinline__ void mbar_wait(uint32_t bar, uint32_t parity) {
  uint32_t ok;
  int spins = 0;
  do {
    if (WAIT_NS)
      asm volatile("{\n.reg .pred p;\nmbarrier.try_wait.parity.shared::cta.b64 p, [%1], %2, %3;\nselp.b32 %0, 1, 0, p;\n}"
                   : "=r"(ok) : "r"(bar), "r"(parity), "r"(WAIT_NS) : "memory");
    else
      asm volatile("{\n.reg .pred p;\nmbarrier.try_wait.parity.shared::cta.b64 p, [%1], %2;\nselp.b32 %0, 1, 0, p;\n}"
                   : "=r"(ok) : "r"(bar), "r"(parity) : "memory");
    if (++spins > SPIN_LIMIT) break;
  } while (!ok);
}
__device__ __forceinline__ unsigned flag_read(const unsigned* p) {
  unsigned v;
  asm volatile("ld.relaxed.gpu.global.u32 %0, [%1];" : "=r"(v) : "l"(p) : "memory");
  return v;
}
__device__ __forceinline__ void flag_poll(const unsigned* p, unsigned target) {
  unsigned v;
  int spins = 0;
  do {
    if (POLL_NS && spins) __nanosleep(POLL_NS);
    asm volatile("ld.relaxed.gpu.global.u32 %0, [%1];" : "=r"(v) : "l"(p) : "memory");
    if (++spins > SPIN_LIMIT) break;
  } while ((int)(v - target) < 0);
}
__device__ __forceinline__ void flag_wait(const unsigned* p, unsigned target) {
  flag_poll(p, target);
  if (ACQ) asm volatile("fence.acquire.gpu;\nfence.proxy.async.global;" ::: "memory");
}
__device__ __forceinline__ void flag_signal(unsigned* p, int n, int lane) {
  if (lane == 0) asm volatile("fence.release.gpu;" ::: "memory");
  __syncwarp();
  if (lane < n) asm volatile("red.relaxed.gpu.global.add.u32 [%0], 1;" ::"l"(p + 32 * lane) : "memory");
}
__device__ __forceinline__ void flag_bump(unsigned* p) {
  asm volatile("red.relaxed.gpu.global.add.u32 [%0], 1;" ::"l"(p) : "memory");
}
__device__ __forceinline__ void fence_async_smem() { asm volatile("fence.proxy.async.shared::cta;" ::: "memory"); }
__device__ __forceinline__ void wg_sync(int id) { asm volatile("bar.sync %0, 128;" ::"r"(id) : "memory"); }

__device__ __forceinline__ void tma_2d(uint32_t dst, const CUtensorMap* tm, int c0, int c1, uint32_t bar) {
  asm volatile("cp.async.bulk.tensor.2d.shared::cluster.global.mbarrier::complete_tx::bytes [%0], [%1, {%3, %4}], [%2];"
               ::"r"(dst), "l"(tm), "r"(bar), "r"(c0), "r"(c1) : "memory");
}
__device__ __forceinline__ void tma_3d(uint32_t dst, const CUtensorMap* tm, int c0, int c1, int c2, uint32_t bar) {
  asm volatile("cp.async.bulk.tensor.3d.shared::cluster.global.mbarrier::complete_tx::bytes [%0], [%1, {%3, %4, %5}], [%2];"
               ::"r"(dst), "l"(tm), "r"(bar), "r"(c0), "r"(c1), "r"(c2) : "memory");
}
__device__ __forceinline__ void bulk_load(uint32_t dst, const void* src, uint32_t bytes, uint32_t bar) {
  asm volatile("cp.async.bulk.shared::cluster.global.mbarrier::complete_tx::bytes [%0], [%1], %2, [%3];"
               ::"r"(dst), "l"(src), "r"(bytes), "r"(bar) : "memory");
}
__device__ __forceinline__ void tm_prefetch(const CUtensorMap* tm) {
  asm volatile("prefetch.tensormap [%0];" ::"l"(tm) : "memory");
}

__device__ __forceinline__ void wg_fence() { asm volatile("wgmma.fence.sync.aligned;" ::: "memory"); }
__device__ __forceinline__ void wg_commit() { asm volatile("wgmma.commit_group.sync.aligned;" ::: "memory"); }
template <int N> __device__ __forceinline__ void wg_wait() { asm volatile("wgmma.wait_group.sync.aligned %0;" ::"n"(N) : "memory"); }
__device__ __forceinline__ uint32_t desc_lo(uint32_t addr, uint32_t lbo) { return ((addr & 0x3FFFF) >> 4) | ((lbo >> 4) << 16); }
constexpr uint32_t desc_hi(uint32_t sbo, uint32_t swz) { return (sbo >> 4) | (swz << 30); }
constexpr uint32_t HI_SW128 = desc_hi(1024, 1), HI_SW64 = desc_hi(512, 2), HI_SW32 = desc_hi(256, 3), HI_NONE = desc_hi(128, 0);
template <int N> __device__ __forceinline__ void pin(float* d) {
#pragma unroll
  for (int i = 0; i < N; i++) asm volatile("" : "+f"(d[i])::"memory");
}

__device__ __forceinline__ uint32_t lds32(uint32_t a) {
  uint32_t v;
  asm volatile("ld.volatile.shared.u32 %0, [%1];" : "=r"(v) : "r"(a) : "memory");
  return v;
}
__device__ __forceinline__ uint4 ldg128(const void* a) {
  uint4 v;
  asm volatile("ld.global.nc.v4.u32 {%0, %1, %2, %3}, [%4];" : "=r"(v.x), "=r"(v.y), "=r"(v.z), "=r"(v.w) : "l"(a) : "memory");
  return v;
}
__device__ __forceinline__ uint2 ldg64(const void* a) {
  uint2 v;
  asm volatile("ld.global.nc.v2.u32 {%0, %1}, [%2];" : "=r"(v.x), "=r"(v.y) : "l"(a) : "memory");
  return v;
}
__device__ __forceinline__ void ldsm4(uint32_t* r, uint32_t a) {
  asm volatile("ldmatrix.sync.aligned.m8n8.x4.shared.b16 {%0, %1, %2, %3}, [%4];"
               : "=r"(r[0]), "=r"(r[1]), "=r"(r[2]), "=r"(r[3]) : "r"(a) : "memory");
}
__device__ __forceinline__ void ldsm4t(uint32_t* r, uint32_t a) {
  asm volatile("ldmatrix.sync.aligned.m8n8.x4.trans.shared.b16 {%0, %1, %2, %3}, [%4];"
               : "=r"(r[0]), "=r"(r[1]), "=r"(r[2]), "=r"(r[3]) : "r"(a) : "memory");
}
__device__ __forceinline__ uint2 lds64(uint32_t a) {
  uint2 v;
  asm volatile("ld.shared.v2.u32 {%0, %1}, [%2];" : "=r"(v.x), "=r"(v.y) : "r"(a) : "memory");
  return v;
}
__device__ __forceinline__ uint4 lds128(uint32_t a) {
  uint4 v;
  asm volatile("ld.shared.v4.u32 {%0, %1, %2, %3}, [%4];" : "=r"(v.x), "=r"(v.y), "=r"(v.z), "=r"(v.w) : "r"(a) : "memory");
  return v;
}
__device__ __forceinline__ void sts128(uint32_t a, uint32_t x, uint32_t y, uint32_t z, uint32_t w) {
  asm volatile("st.shared.v4.u32 [%0], {%1, %2, %3, %4};" ::"r"(a), "r"(x), "r"(y), "r"(z), "r"(w) : "memory");
}
__device__ __forceinline__ void stsm4(uint32_t a, const uint32_t* r) {
  asm volatile("stmatrix.sync.aligned.m8n8.x4.shared.b16 [%0], {%1, %2, %3, %4};" ::"r"(a), "r"(r[0]), "r"(r[1]), "r"(r[2]), "r"(r[3]) : "memory");
}
__device__ __forceinline__ void stsm4t(uint32_t a, const uint32_t* r) {
  asm volatile("stmatrix.sync.aligned.m8n8.x4.trans.shared.b16 [%0], {%1, %2, %3, %4};" ::"r"(a), "r"(r[0]), "r"(r[1]), "r"(r[2]), "r"(r[3]) : "memory");
}
__device__ __forceinline__ uint32_t pack2(float lo, float hi) {
  uint32_t r;
  asm("cvt.rn.bf16x2.f32 %0, %1, %2;" : "=r"(r) : "f"(hi), "f"(lo));
  return r;
}
__device__ __forceinline__ uint32_t movm(uint32_t a) {
  uint32_t d;
  asm volatile("movmatrix.sync.aligned.m8n8.trans.b16 %0, %1;" : "=r"(d) : "r"(a));
  return d;
}
__device__ __forceinline__ uint32_t bmul(uint32_t a, uint32_t b) {
  uint32_t d;
  asm("mul.rn.bf16x2 %0, %1, %2;" : "=r"(d) : "r"(a), "r"(b));
  return d;
}
__device__ __forceinline__ uint32_t badd(uint32_t a, uint32_t b) {
  uint32_t d;
  asm("add.rn.bf16x2 %0, %1, %2;" : "=r"(d) : "r"(a), "r"(b));
  return d;
}
__device__ __forceinline__ uint32_t bfma(uint32_t a, uint32_t b, uint32_t c) {
  uint32_t d;
  asm("fma.rn.bf16x2 %0, %1, %2, %3;" : "=r"(d) : "r"(a), "r"(b), "r"(c));
  return d;
}
__device__ __forceinline__ float bf_lo(uint32_t x) { return __uint_as_float(x << 16); }
__device__ __forceinline__ float bf_hi(uint32_t x) { return __uint_as_float(x & 0xFFFF0000u); }
__device__ __forceinline__ float ex2(float x) {
  float y;
  asm("ex2.approx.ftz.f32 %0, %1;" : "=f"(y) : "f"(x));
  return y;
}
__device__ __forceinline__ float rcp(float x) {
  float y;
  asm("rcp.approx.ftz.f32 %0, %1;" : "=f"(y) : "f"(x));
  return y;
}
__device__ __forceinline__ void mma16816(float* d, uint32_t a0, uint32_t a1, uint32_t a2, uint32_t a3, uint32_t b0, uint32_t b1) {
  asm volatile("mma.sync.aligned.m16n8k16.row.col.f32.bf16.bf16.f32 {%0, %1, %2, %3}, {%4, %5, %6, %7}, {%8, %9}, {%0, %1, %2, %3};"
               : "+f"(d[0]), "+f"(d[1]), "+f"(d[2]), "+f"(d[3])
               : "r"(a0), "r"(a1), "r"(a2), "r"(a3), "r"(b0), "r"(b1));
}
__device__ __forceinline__ void mma1688(float* d, uint32_t a0, uint32_t a1, uint32_t b0) {
  asm volatile("mma.sync.aligned.m16n8k8.row.col.f32.bf16.bf16.f32 {%0, %1, %2, %3}, {%4, %5}, {%6}, {%0, %1, %2, %3};"
               : "+f"(d[0]), "+f"(d[1]), "+f"(d[2]), "+f"(d[3])
               : "r"(a0), "r"(a1), "r"(b0));
}

template <int N> struct WgRS;
template <int N> struct WgSST;
template <> struct WgRS<32> {
  template <uint32_t HB>
  static __device__ __forceinline__ void mma(float* d, const uint32_t* a, uint32_t db) {
    asm volatile("{\n.reg .pred p;\n.reg .b64 db;\nsetp.ne.b32 p, %22, 0;\n"
      "mov.b64 db, {%20, %21};\n"
      "wgmma.mma_async.sync.aligned.m64n32k16.f32.bf16.bf16 {"
      "%0, %1, %2, %3, %4, %5, %6, %7, %8, %9, %10, %11, %12, %13, %14, %15"
      "}, {%16, %17, %18, %19}, db, p, 1, 1, 1;\n}\n"
      : "+f"(d[0]), "+f"(d[1]), "+f"(d[2]), "+f"(d[3]), "+f"(d[4]), "+f"(d[5]), "+f"(d[6]), "+f"(d[7]),
        "+f"(d[8]), "+f"(d[9]), "+f"(d[10]), "+f"(d[11]), "+f"(d[12]), "+f"(d[13]), "+f"(d[14]), "+f"(d[15])
      : "r"(a[0]), "r"(a[1]), "r"(a[2]), "r"(a[3]), "r"(db), "n"(HB), "n"(1));
  }
  template <uint32_t HB>
  static __device__ __forceinline__ void set(float* d, const uint32_t* a, uint32_t db) {
    asm volatile("{\n.reg .pred p;\n.reg .b64 db;\nsetp.ne.b32 p, %22, 0;\n"
      "mov.b64 db, {%20, %21};\n"
      "wgmma.mma_async.sync.aligned.m64n32k16.f32.bf16.bf16 {"
      "%0, %1, %2, %3, %4, %5, %6, %7, %8, %9, %10, %11, %12, %13, %14, %15"
      "}, {%16, %17, %18, %19}, db, p, 1, 1, 1;\n}\n"
      : "=f"(d[0]), "=f"(d[1]), "=f"(d[2]), "=f"(d[3]), "=f"(d[4]), "=f"(d[5]), "=f"(d[6]), "=f"(d[7]),
        "=f"(d[8]), "=f"(d[9]), "=f"(d[10]), "=f"(d[11]), "=f"(d[12]), "=f"(d[13]), "=f"(d[14]), "=f"(d[15])
      : "r"(a[0]), "r"(a[1]), "r"(a[2]), "r"(a[3]), "r"(db), "n"(HB), "n"(0));
  }
};
template <> struct WgRS<64> {
  template <uint32_t HB>
  static __device__ __forceinline__ void mma(float* d, const uint32_t* a, uint32_t db) {
    asm volatile("{\n.reg .pred p;\n.reg .b64 db;\nsetp.ne.b32 p, %38, 0;\n"
      "mov.b64 db, {%36, %37};\n"
      "wgmma.mma_async.sync.aligned.m64n64k16.f32.bf16.bf16 {"
      "%0, %1, %2, %3, %4, %5, %6, %7, %8, %9, %10, %11, %12, %13, %14, %15, "
      "%16, %17, %18, %19, %20, %21, %22, %23, %24, %25, %26, %27, %28, %29, %30, %31"
      "}, {%32, %33, %34, %35}, db, p, 1, 1, 1;\n}\n"
      : "+f"(d[0]), "+f"(d[1]), "+f"(d[2]), "+f"(d[3]), "+f"(d[4]), "+f"(d[5]), "+f"(d[6]), "+f"(d[7]),
        "+f"(d[8]), "+f"(d[9]), "+f"(d[10]), "+f"(d[11]), "+f"(d[12]), "+f"(d[13]), "+f"(d[14]), "+f"(d[15]),
        "+f"(d[16]), "+f"(d[17]), "+f"(d[18]), "+f"(d[19]), "+f"(d[20]), "+f"(d[21]), "+f"(d[22]), "+f"(d[23]),
        "+f"(d[24]), "+f"(d[25]), "+f"(d[26]), "+f"(d[27]), "+f"(d[28]), "+f"(d[29]), "+f"(d[30]), "+f"(d[31])
      : "r"(a[0]), "r"(a[1]), "r"(a[2]), "r"(a[3]), "r"(db), "n"(HB), "n"(1));
  }
  template <uint32_t HB>
  static __device__ __forceinline__ void set(float* d, const uint32_t* a, uint32_t db) {
    asm volatile("{\n.reg .pred p;\n.reg .b64 db;\nsetp.ne.b32 p, %38, 0;\n"
      "mov.b64 db, {%36, %37};\n"
      "wgmma.mma_async.sync.aligned.m64n64k16.f32.bf16.bf16 {"
      "%0, %1, %2, %3, %4, %5, %6, %7, %8, %9, %10, %11, %12, %13, %14, %15, "
      "%16, %17, %18, %19, %20, %21, %22, %23, %24, %25, %26, %27, %28, %29, %30, %31"
      "}, {%32, %33, %34, %35}, db, p, 1, 1, 1;\n}\n"
      : "=f"(d[0]), "=f"(d[1]), "=f"(d[2]), "=f"(d[3]), "=f"(d[4]), "=f"(d[5]), "=f"(d[6]), "=f"(d[7]),
        "=f"(d[8]), "=f"(d[9]), "=f"(d[10]), "=f"(d[11]), "=f"(d[12]), "=f"(d[13]), "=f"(d[14]), "=f"(d[15]),
        "=f"(d[16]), "=f"(d[17]), "=f"(d[18]), "=f"(d[19]), "=f"(d[20]), "=f"(d[21]), "=f"(d[22]), "=f"(d[23]),
        "=f"(d[24]), "=f"(d[25]), "=f"(d[26]), "=f"(d[27]), "=f"(d[28]), "=f"(d[29]), "=f"(d[30]), "=f"(d[31])
      : "r"(a[0]), "r"(a[1]), "r"(a[2]), "r"(a[3]), "r"(db), "n"(HB), "n"(0));
  }
};
template <> struct WgSST<48> {
  template <uint32_t HA, uint32_t HB>
  static __device__ __forceinline__ void mma(float* d, uint32_t da, uint32_t db, int sc) {
    asm volatile("{\n.reg .pred p;\n.reg .b64 da, db;\nsetp.ne.b32 p, %28, 0;\n"
      "mov.b64 da, {%24, %25};\nmov.b64 db, {%26, %27};\n"
      "wgmma.mma_async.sync.aligned.m64n48k16.f32.bf16.bf16 {"
      "%0, %1, %2, %3, %4, %5, %6, %7, %8, %9, %10, %11, %12, %13, %14, %15, "
      "%16, %17, %18, %19, %20, %21, %22, %23"
      "}, da, db, p, 1, 1, 0, 1;\n}\n"
      : "+f"(d[0]), "+f"(d[1]), "+f"(d[2]), "+f"(d[3]), "+f"(d[4]), "+f"(d[5]), "+f"(d[6]), "+f"(d[7]),
        "+f"(d[8]), "+f"(d[9]), "+f"(d[10]), "+f"(d[11]), "+f"(d[12]), "+f"(d[13]), "+f"(d[14]), "+f"(d[15]),
        "+f"(d[16]), "+f"(d[17]), "+f"(d[18]), "+f"(d[19]), "+f"(d[20]), "+f"(d[21]), "+f"(d[22]), "+f"(d[23])
      : "r"(da), "n"(HA), "r"(db), "n"(HB), "r"(sc));
  }
};
template <> struct WgSST<80> {
  template <uint32_t HA, uint32_t HB>
  static __device__ __forceinline__ void mma(float* d, uint32_t da, uint32_t db, int sc) {
    asm volatile("{\n.reg .pred p;\n.reg .b64 da, db;\nsetp.ne.b32 p, %44, 0;\n"
      "mov.b64 da, {%40, %41};\nmov.b64 db, {%42, %43};\n"
      "wgmma.mma_async.sync.aligned.m64n80k16.f32.bf16.bf16 {"
      "%0, %1, %2, %3, %4, %5, %6, %7, %8, %9, %10, %11, %12, %13, %14, %15, "
      "%16, %17, %18, %19, %20, %21, %22, %23, %24, %25, %26, %27, %28, %29, %30, %31, "
      "%32, %33, %34, %35, %36, %37, %38, %39"
      "}, da, db, p, 1, 1, 0, 1;\n}\n"
      : "+f"(d[0]), "+f"(d[1]), "+f"(d[2]), "+f"(d[3]), "+f"(d[4]), "+f"(d[5]), "+f"(d[6]), "+f"(d[7]),
        "+f"(d[8]), "+f"(d[9]), "+f"(d[10]), "+f"(d[11]), "+f"(d[12]), "+f"(d[13]), "+f"(d[14]), "+f"(d[15]),
        "+f"(d[16]), "+f"(d[17]), "+f"(d[18]), "+f"(d[19]), "+f"(d[20]), "+f"(d[21]), "+f"(d[22]), "+f"(d[23]),
        "+f"(d[24]), "+f"(d[25]), "+f"(d[26]), "+f"(d[27]), "+f"(d[28]), "+f"(d[29]), "+f"(d[30]), "+f"(d[31]),
        "+f"(d[32]), "+f"(d[33]), "+f"(d[34]), "+f"(d[35]), "+f"(d[36]), "+f"(d[37]), "+f"(d[38]), "+f"(d[39])
      : "r"(da), "n"(HA), "r"(db), "n"(HB), "r"(sc));
  }
};
template <> struct WgSST<192> {
  template <uint32_t HA, uint32_t HB>
  static __device__ __forceinline__ void mma(float* d, uint32_t da, uint32_t db, int sc) {
    asm volatile("{\n.reg .pred p;\n.reg .b64 da, db;\nsetp.ne.b32 p, %100, 0;\n"
      "mov.b64 da, {%96, %97};\nmov.b64 db, {%98, %99};\n"
      "wgmma.mma_async.sync.aligned.m64n192k16.f32.bf16.bf16 {"
      "%0, %1, %2, %3, %4, %5, %6, %7, %8, %9, %10, %11, %12, %13, %14, %15, "
      "%16, %17, %18, %19, %20, %21, %22, %23, %24, %25, %26, %27, %28, %29, %30, %31, "
      "%32, %33, %34, %35, %36, %37, %38, %39, %40, %41, %42, %43, %44, %45, %46, %47, "
      "%48, %49, %50, %51, %52, %53, %54, %55, %56, %57, %58, %59, %60, %61, %62, %63, "
      "%64, %65, %66, %67, %68, %69, %70, %71, %72, %73, %74, %75, %76, %77, %78, %79, "
      "%80, %81, %82, %83, %84, %85, %86, %87, %88, %89, %90, %91, %92, %93, %94, %95"
      "}, da, db, p, 1, 1, 0, 1;\n}\n"
      : "+f"(d[0]), "+f"(d[1]), "+f"(d[2]), "+f"(d[3]), "+f"(d[4]), "+f"(d[5]), "+f"(d[6]), "+f"(d[7]),
        "+f"(d[8]), "+f"(d[9]), "+f"(d[10]), "+f"(d[11]), "+f"(d[12]), "+f"(d[13]), "+f"(d[14]), "+f"(d[15]),
        "+f"(d[16]), "+f"(d[17]), "+f"(d[18]), "+f"(d[19]), "+f"(d[20]), "+f"(d[21]), "+f"(d[22]), "+f"(d[23]),
        "+f"(d[24]), "+f"(d[25]), "+f"(d[26]), "+f"(d[27]), "+f"(d[28]), "+f"(d[29]), "+f"(d[30]), "+f"(d[31]),
        "+f"(d[32]), "+f"(d[33]), "+f"(d[34]), "+f"(d[35]), "+f"(d[36]), "+f"(d[37]), "+f"(d[38]), "+f"(d[39]),
        "+f"(d[40]), "+f"(d[41]), "+f"(d[42]), "+f"(d[43]), "+f"(d[44]), "+f"(d[45]), "+f"(d[46]), "+f"(d[47]),
        "+f"(d[48]), "+f"(d[49]), "+f"(d[50]), "+f"(d[51]), "+f"(d[52]), "+f"(d[53]), "+f"(d[54]), "+f"(d[55]),
        "+f"(d[56]), "+f"(d[57]), "+f"(d[58]), "+f"(d[59]), "+f"(d[60]), "+f"(d[61]), "+f"(d[62]), "+f"(d[63]),
        "+f"(d[64]), "+f"(d[65]), "+f"(d[66]), "+f"(d[67]), "+f"(d[68]), "+f"(d[69]), "+f"(d[70]), "+f"(d[71]),
        "+f"(d[72]), "+f"(d[73]), "+f"(d[74]), "+f"(d[75]), "+f"(d[76]), "+f"(d[77]), "+f"(d[78]), "+f"(d[79]),
        "+f"(d[80]), "+f"(d[81]), "+f"(d[82]), "+f"(d[83]), "+f"(d[84]), "+f"(d[85]), "+f"(d[86]), "+f"(d[87]),
        "+f"(d[88]), "+f"(d[89]), "+f"(d[90]), "+f"(d[91]), "+f"(d[92]), "+f"(d[93]), "+f"(d[94]), "+f"(d[95])
      : "r"(da), "n"(HA), "r"(db), "n"(HB), "r"(sc));
  }
};

struct FftConst {
  uint32_t f[2][4], fi[4][4];
  uint32_t ta[2][2], tb[2][2];
};
__device__ __forceinline__ void cis(int m, float scale, float& c, float& s) {
  const float a = (float)m * (-6.283185307179586f * scale);
  c = __cosf(a);
  s = __sinf(a);
}
__device__ __forceinline__ void fft_tables(uint32_t (&v)[12], int tw) {
  const int row = tw >> 2, ch = tw & 3;
#pragma unroll
  for (int i = 0; i < 4; i++) {
    float c[2], s[2], x[2];
#pragma unroll
    for (int e = 0; e < 2; e++) {
      cis((((32 * (8 * ch + 2 * i + e) + 15) * (4 * row - 63) + 2048) & 4095) - 2048, 1.f / 4096, c[e], s[e]);
      float gc, gs;
      cis((((row & 15) * (8 * (ch & 1) + 2 * i + e) + 8) & 15) - 8, 1.f / 16, gc, gs);
      x[e] = (row >> 4) == (ch >> 1) ? gc : (ch >> 1) ? gs : -gs;
    }
    v[i] = pack2(c[0] * 0.125f, c[1] * 0.125f);
    v[4 + i] = pack2(s[0] * 0.125f, s[1] * 0.125f);
    v[8 + i] = pack2(x[0], x[1]);
  }
#pragma unroll
  for (int i = 0; i < 12; i++) asm volatile("" : "+r"(v[i]));
}
__device__ __forceinline__ void fft_tables_store(const uint32_t (&v)[12], uint32_t sb, int tw) {
  const int row = tw >> 2;
  const uint32_t x = ((tw ^ (row >> 1)) & 3) << 4, a = sb + OFF_FT + (16 * (row >> 3) + (row & 7)) * 64 + x;
  sts128(a, v[0], v[1], v[2], v[3]);
  sts128(a + 512, v[4], v[5], v[6], v[7]);
  sts128(sb + OFF_GT + row * 64 + x, v[8], v[9], v[10], v[11]);
}
__device__ __forceinline__ void fft_twiddles(uint32_t (&v)[2], int tw) {
  float a[2], s[2];
#pragma unroll
  for (int i = 0; i < 2; i++) {
    float c;
    cis((2 * (2 * (tw & 3) + i) - 15) * (4 * (tw >> 2) - 63), 1.f / 4096, c, s[i]);
    a[i] = __fdividef(-s[i], 1.f + c);
  }
  v[0] = pack2(a[0], a[1]);
  v[1] = pack2(s[0], s[1]);
  asm volatile("" : "+r"(v[0]), "+r"(v[1]));
}
__device__ __forceinline__ void fft_matrices(FftConst& k, uint32_t sb, int w, int lane) {
  const uint32_t x = (lane >> 1) & 3;
  const uint2 t0 = lds64(sb + OFF_TT + 256 * w + 8 * lane), t1 = lds64(sb + OFF_TT + 256 * w + 8 * (lane ^ 3));
  k.ta[0][0] = t0.x;
  k.tb[0][0] = t0.y;
  k.ta[1][1] = __byte_perm(t1.x, 0, 0x1032);
  k.tb[1][1] = __byte_perm(t1.y, 0, 0x1032);
#pragma unroll
  for (int j = 0; j < 2; j++) {
    k.ta[1 - j][j] = k.ta[j][j] ^ 0x80008000u;
    k.tb[1 - j][j] = k.tb[j][j] ^ 0x80008000u;
    asm volatile("" : "+r"(k.ta[0][j]), "+r"(k.tb[0][j]), "+r"(k.ta[1][j]), "+r"(k.tb[1][j]));
  }
#pragma unroll
  for (int i = 0; i < 2; i++) {
    ldsm4(k.f[i], sb + OFF_FT + (16 * w + (lane & 15)) * 64 + (((2 * i + (lane >> 4)) ^ x) << 4));
    ldsm4t(k.fi[i], sb + OFF_FT + (32 * i + lane) * 64 + ((w ^ x) << 4));
#pragma unroll
    for (int j = 0; j < 4; j++) {
      k.fi[2 + i][j] = (j & 1) ? k.fi[i][j - 1] ^ 0x80008000u : k.fi[i][j + 1];
      asm volatile("" : "+r"(k.fi[2 + i][j]));
    }
  }
}
__device__ __forceinline__ void rot(uint32_t& x, uint32_t& y, uint32_t a, uint32_t b) {
  x = bfma(a, y, x);
  y = bfma(b, x, y);
  x = bfma(a, y, x);
}
__device__ __forceinline__ void twiddle_fwd(uint32_t (&a)[4][4], float* d, const FftConst& k) {
#pragma unroll
  for (int q = 0; q < 4; q++)
#pragma unroll
    for (int j = 0; j < 2; j++) {
      const float* x = d + 8 * q + 4 * j;
      uint32_t re = pack2(x[0], x[1]), im = pack2(x[2], x[3]);
      rot(re, im, k.ta[0][j], k.tb[0][j]);
      a[q & 2][2 * j + (q & 1)] = re;
      a[(q & 2) + 1][2 * j + (q & 1)] = im;
    }
}
__device__ __forceinline__ void g_step(float* d, const uint32_t (&a)[4][4], uint32_t dre, uint32_t dim) {
  WgRS<32>::set<HI_SW64>(d, a[0], dre);
  WgRS<32>::set<HI_SW64>(d + 16, a[2], dre);
  WgRS<32>::mma<HI_SW64>(d, a[1], dim);
  WgRS<32>::mma<HI_SW64>(d + 16, a[3], dim);
  wg_commit();
}

__device__ __forceinline__ void conv_channel(const FftConst& k, uint32_t sb, int c, int wg, int w, int lane) {
  const uint32_t cb = sb + off_ch(c), bars = sb + OFF_BAR;
  const uint32_t du = desc_lo(cb, 1024), dg = desc_lo(sb + OFF_GT, 16), dz = desc_lo(cb + U_BYTES, 16);
  float U[32], H[32];
  uint32_t a[4][4], e[4][4];
  const float dv = __uint_as_float(lds32(sb + OFF_D + 4 * c));
  wg_fence();
  WgRS<64>::set<HI_SW32>(H, k.f[0], du + 256);
  WgRS<64>::mma<HI_SW32>(H, k.f[1], du + 256 + 32);
  wg_commit();
  wg_wait<0>();
  pin<32>(H);
  twiddle_fwd(a, H, k);
  if (ATT_GATE) mbar_wait(bars + 8 * (ATT_GATE == 1 ? B_ATTN : B_ATT2), 0);
  mbar_wait(bars + 8 * (B_U + (c < 3 ? c : 3)), 0);
  TSM(w == 0 && c < 3, 7 + wg);
  wg_fence();
  WgRS<64>::set<HI_SW32>(U, k.f[0], du);
  WgRS<64>::mma<HI_SW32>(U, k.f[1], du + 32);
  wg_commit();
  g_step(H, a, dg, dg + 64);
  wg_wait<1>();
  pin<32>(U);
  twiddle_fwd(e, U, k);
  wg_fence();
  g_step(U, e, dg, dg + 64);
  wg_wait<0>();
  pin<32>(U);
  pin<32>(H);
#pragma unroll
  for (int j = 0; j < 2; j++) {
    float pr[4][2], pi[4][2];
#pragma unroll
    for (int x = 0; x < 2; x++) {
      H[4 * j + x] += dv;
#pragma unroll
      for (int m = 0; m < 4; m++) {
#pragma unroll
        for (int q = 0; q <= m; q++) {
          const int ih = 16 * (q >> 1) + 2 * (q & 1) + 4 * j + x, iu = 16 * ((m - q) >> 1) + 2 * ((m - q) & 1) + 4 * j + x;
          pr[m][x] = q ? fmaf(H[ih], U[iu], pr[m][x]) : H[ih] * U[iu];
          pi[m][x] = q ? fmaf(H[ih], U[iu + 8], pi[m][x]) : H[ih] * U[iu + 8];
          pr[m][x] = fmaf(-H[ih + 8], U[iu + 8], pr[m][x]);
          pi[m][x] = fmaf(H[ih + 8], U[iu], pi[m][x]);
        }
      }
    }
#pragma unroll
    for (int m = 0; m < 4; m++) {
      a[m & 2][2 * j + (m & 1)] = pack2(pr[m][0], pr[m][1]);
      a[(m & 2) + 1][2 * j + (m & 1)] = pack2(pi[m][0], pi[m][1]);
    }
  }
  wg_fence();
  g_step(U, a, dg + 64, dg);
  const uint32_t za = cb + U_BYTES + (8 * w + (lane & 7)) * 128 + (((lane >> 3) ^ (lane & 7)) << 4);
  const uint32_t ya = cb + (lane >> 4) * 1024 + (8 * w + (lane & 7)) * 32 + ((((lane >> 3) ^ (lane >> 2)) & 1) << 4);
  wg_sync(1 + wg);
  wg_wait<0>();
  pin<32>(U);
  TSIF(w == 0, 80 + c);
#pragma unroll
  for (int p = 0; p < 2; p++) {
#pragma unroll
    for (int i = 0; i < 4; i++) {
      const int j = i & 1;
      const float* x = U + 16 * p + 4 * j + (i & 2);
      e[p][i] = pack2(x[8], x[9]);
      e[2 + p][i] = pack2(x[0], x[1]);
      rot(e[p][i], e[2 + p][i], k.ta[1][j], k.tb[1][j]);
    }
    stsm4(za ^ (64 * p), e[p]);
    stsm4((za ^ (64 * p)) + 4096, e[2 + p]);
  }
  fence_async_smem();
  wg_sync(1 + wg);
  wg_fence();
  WgRS<64>::set<HI_SW128>(H, k.fi[0], dz);
#pragma unroll
  for (int ks = 1; ks < 4; ks++) WgRS<64>::mma<HI_SW128>(H, k.fi[ks], dz + 128 * ks);
  wg_commit();
  if (WO_FAST) mbar_wait(bars + 8 * B_ATTN, 0);
  wg_wait<0>();
  pin<32>(H);
  TSIF(w == 0, 88 + c);
#pragma unroll
  for (int j = 0; j < 8; j++)
    a[j >> 2][j & 3] = j < 2 ? pack2(H[4 * j], H[4 * j + 1]) : pack2(H[4 * j] + H[4 * j - 6], H[4 * j + 1] + H[4 * j - 5]);
  stsm4(ya, a[0]);
  stsm4(ya + 2048, a[1]);
  fence_async_smem();
  __syncwarp();
}

__device__ __forceinline__ void prep_slab(uint4* res, const uint2* sw, uint32_t sb, int slab, int w, int lane) {
  const int t = lane & 3, tp = (lane & 7) >> 1, pos = 8 * tp + 2 * (((lane >> 3) + tp) & 3) + (lane & 1);
  const uint32_t base = sb + OFF_KVS + slab * KVS_BYTES + pos * 128;
  uint32_t kk[2][4][4], vv[2][4];
  mbar_wait(sb + OFF_BAR + 8 * (B_KV + slab), 0);
#pragma unroll
  for (int h = 0; h < 2; h++) {
#pragma unroll
    for (int j = 0; j < 4; j++) {
      const uint32_t a = base + 128 * j;
      ldsm4t(kk[h][j], a + (((w + 4 * h) ^ ((a >> 7) & 7)) << 4));
    }
    const uint32_t a = base + KVS_V;
    ldsm4t(vv[h], a + (((w + 4 * h) ^ ((a >> 7) & 7)) << 4));
  }
#pragma unroll
  for (int h = 0; h < 2; h++) {
    uint32_t (&k)[4][4] = kk[h];
    uint32_t (&v)[4] = vv[h];
    const uint32_t w0 = __byte_perm(sw[h].x, 0, 0x1010), w1 = __byte_perm(sw[h].x, 0, 0x3232);
    const uint32_t w2 = __byte_perm(sw[h].y, 0, 0x1010), w3 = __byte_perm(sw[h].y, 0, 0x3232);
#pragma unroll
    for (int m = 0; m < 4; m++)
      v[m] = bmul(badd(badd(badd(bmul(k[0][m], w3), bmul(k[1][m], w2)), bmul(k[2][m], w1)), bmul(k[3][m], w0)), v[m]);
    uint32_t a[4];
#pragma unroll
    for (int m = 0; m < 4; m++) a[m] = (t & 1) ? v[(m + 3) & 3] : v[m];
    res[h] = (t & 2) ? make_uint4(a[2], a[3], a[0], a[1]) : make_uint4(a[0], a[1], a[2], a[3]);
  }
}

__device__ __forceinline__ void prep_gate(const Params& p, int b, int w, int lane) {
  uint2 gw[5], x[4][5];
#pragma unroll
  for (int j = 0; j < 5; j++) gw[j] = ldg64(reinterpret_cast<const uint2*>(p.gate_w) + lane + 32 * j);
#pragma unroll
  for (int i = 0; i < 4; i++)
#pragma unroll
    for (int j = 0; j < 5; j++)
      x[i][j] = ldg64(reinterpret_cast<const uint2*>(p.q) + (16 * b + 4 * w + i) * (DIM / 4) + lane + 32 * j);
  float s[4];
#pragma unroll
  for (int i = 0; i < 4; i++) {
    s[i] = 0.f;
#pragma unroll
    for (int j = 0; j < 5; j++) {
      const uint32_t m0 = bmul(x[i][j].x, gw[j].x), m1 = bmul(x[i][j].y, gw[j].y);
      s[i] += (bf_lo(m0) + bf_hi(m0)) + (bf_lo(m1) + bf_hi(m1));
    }
  }
  const bool h = lane & 16, q = lane & 8;
  const float a = (h ? s[2] : s[0]) + __shfl_xor_sync(0xffffffffu, h ? s[0] : s[2], 16);
  const float c = (h ? s[3] : s[1]) + __shfl_xor_sync(0xffffffffu, h ? s[1] : s[3], 16);
  float z = (q ? c : a) + __shfl_xor_sync(0xffffffffu, q ? a : c, 8);
#pragma unroll
  for (int o = 4; o > 0; o >>= 1) z += __shfl_xor_sync(0xffffffffu, z, o);
  z = bf_lo(pack2(z, 0.f));
  if ((lane & 7) == 0) g_gate[16 * b + 4 * w + (lane >> 3)] = bf_lo(pack2(__fdividef(1.f, 1.f + __expf(-z)), 0.f));
}

__device__ __forceinline__ uint32_t bmax(uint32_t a, uint32_t b) {
  uint32_t d;
  asm("max.bf16x2 %0, %1, %2;" : "=r"(d) : "r"(a), "r"(b));
  return d;
}
__device__ __forceinline__ void softmax_two(const float (&l)[2][2], uint32_t& p0, uint32_t& p1) {
  constexpr float kScale = 0.22360679774997896f, kLog2e = 1.4426950408889634f;
  const uint32_t r0 = pack2(l[0][0], l[1][0]), r1 = pack2(l[0][1], l[1][1]);
  const uint32_t x0 = pack2(bf_lo(r0) * kScale, bf_hi(r0) * kScale), x1 = pack2(bf_lo(r1) * kScale, bf_hi(r1) * kScale);
  uint32_t m = bmax(x0, x1);
  m = bmax(m, __shfl_xor_sync(0xffffffffu, m, 1));
  m = bmax(m, __shfl_xor_sync(0xffffffffu, m, 2));
  const float m0 = bf_lo(m) * kLog2e, m1 = bf_hi(m) * kLog2e;
  p0 = pack2(ex2(bf_lo(x0) * kLog2e - m0), ex2(bf_lo(x1) * kLog2e - m0));
  p1 = pack2(ex2(bf_hi(x0) * kLog2e - m1), ex2(bf_hi(x1) * kLog2e - m1));
}

__device__ __forceinline__ void halo_read(uint32_t (&kpv)[10], uint32_t (&vpv)[10], uint32_t (&tg)[7], const uint4* hp) {
#pragma unroll
  for (int j = 0; j < 7; j++) {
    uint32_t x0, x1, x2;
    asm volatile("ld.relaxed.gpu.global.v4.u32 {%0, %1, %2, %3}, [%4];"
                 : "=r"(x0), "=r"(x1), "=r"(x2), "=r"(tg[j]) : "l"(hp + 32 * j) : "memory");
    if (j < 4) kpv[3 * j] = x0; else vpv[3 * j - 10] = x0;
    if (j < 3) kpv[3 * j + 1] = x1; else vpv[3 * j - 9] = x1;
    if (j < 3) kpv[3 * j + 2] = x2; else if (j < 6) vpv[3 * j - 8] = x2;
  }
}

template <int ROT>
__device__ __forceinline__ void pack_qkv(const float* acc, uint32_t (&qlo)[10], uint32_t (&qhi)[10], uint32_t (&klo)[10],
                                         uint32_t (&khi)[10], uint32_t (&vlo)[10], uint32_t (&vhi)[10]) {
#pragma unroll
  for (int j = 0; j < 10; j++) {
    const int x = (j + ROT) % 10, tq = x < 8 ? x : 16 + x, tk = x < 8 ? 8 + x : 18 + x, tv = x < 8 ? 16 + x : 20 + x;
    khi[j] = pack2(acc[4 * tk + 2], acc[4 * tk + 3]);
    vhi[j] = movm(pack2(acc[4 * tv + 2], acc[4 * tv + 3]));
    qlo[j] = pack2(acc[4 * tq], acc[4 * tq + 1]);
    qhi[j] = pack2(acc[4 * tq + 2], acc[4 * tq + 3]);
    klo[j] = pack2(acc[4 * tk], acc[4 * tk + 1]);
    vlo[j] = pack2(acc[4 * tv], acc[4 * tv + 1]);
    asm volatile("" : "+r"(khi[j]), "+r"(qlo[j]), "+r"(qhi[j]), "+r"(klo[j]), "+r"(vlo[j]));
  }
}

template <int ROT> __device__ __forceinline__ void halo_send(const float* acc, uint4* ho, uint32_t tag) {
#pragma unroll
  for (int j = 0; j < 7; j++) {
    uint32_t x[3];
#pragma unroll
    for (int e = 0; e < 3; e++) {
      const int i = 3 * j + e, y = (i % 10 + ROT) % 10, tk = y < 8 ? 8 + y : 18 + y, tv = y < 8 ? 16 + y : 20 + y;
      x[e] = i < 10 ? pack2(acc[4 * tk + 2], acc[4 * tk + 3]) : i < 20 ? movm(pack2(acc[4 * tv + 2], acc[4 * tv + 3])) : 0u;
    }
    asm volatile("st.relaxed.gpu.global.v4.u32 [%0], {%1, %2, %3, %4};" ::"l"(ho + 32 * j), "r"(x[0]), "r"(x[1]), "r"(x[2]), "r"(tag) : "memory");
  }
}

__device__ __forceinline__ void attention(float* acc, uint32_t sb, int b, int par, int w, int lane, uint32_t tag, uint32_t zero) {
  const int g = lane >> 2, t = lane & 3;
  uint32_t klo[10], khi[10], vlo[10], vhi[10], qlo[10], qhi[10], kpv[10], vpv[10];
  if (HALO_FIRST && w == 3 && b < NCTA - 8) {
    uint4* ho = g_halo + (b * 2 + par) * 224 + lane;
    if (tail_first(b & 7)) halo_send<8>(acc, ho, tag);
    else halo_send<0>(acc, ho, tag);
    TSIF(par == 0, 76);
    pin<120>(acc);
  }
  if (tail_first(b & 7)) pack_qkv<8>(acc, qlo, qhi, klo, khi, vlo, vhi);
  else pack_qkv<0>(acc, qlo, qhi, klo, khi, vlo, vhi);
  const uint32_t xa = sb + OFF_KVX + (par * 3) * 2560 + lane * 16;
  if (w < 3) {
    sts128(xa + w * 2560, khi[0], khi[1], khi[2], khi[3]);
    sts128(xa + w * 2560 + 512, khi[4], khi[5], khi[6], khi[7]);
    sts128(xa + w * 2560 + 1024, khi[8], khi[9], vhi[0], vhi[1]);
    sts128(xa + w * 2560 + 1536, vhi[2], vhi[3], vhi[4], vhi[5]);
    sts128(xa + w * 2560 + 2048, vhi[6], vhi[7], vhi[8], vhi[9]);
  } else if (!HALO_FIRST && b < NCTA - 8) {
    uint4* ho = g_halo + (b * 2 + par) * 224 + lane;
#pragma unroll
    for (int j = 0; j < 7; j++) {
      const uint32_t x0 = j < 4 ? khi[3 * j] : vhi[3 * j - 10], x1 = j < 3 ? khi[3 * j + 1] : vhi[3 * j - 9];
      const uint32_t x2 = j < 3 ? khi[3 * j + 2] : j < 6 ? vhi[3 * j - 8] : 0u;
      asm volatile("st.relaxed.gpu.global.v4.u32 [%0], {%1, %2, %3, %4};" ::"l"(ho + 32 * j), "r"(x0), "r"(x1), "r"(x2), "r"(tag) : "memory");
    }
  }
  TSIF(par == 0 && w == 1, 64);
  TSIF(par == 0 && w == 3 && !HALO_FIRST, 76);
#pragma unroll
  for (int j = 0; j < 10; j++) vlo[j] = movm(vlo[j]);
  const bool far0 = 2 * t > g, far1 = 2 * t + 1 > g;
  const uint32_t mfar = (far0 ? 0x0000FFFFu : 0u) | (far1 ? 0xFFFF0000u : 0u);
  float slo[4][2], shi[4][2], lg[2][2];
  uint32_t phi[4], plo[4], qml[4], qmh[4];
#pragma unroll
  for (int h = 0; h < 4; h++) {
    const int f = h == 0 ? 0 : h == 1 ? 3 : h == 2 ? 5 : 8, hf = h < 2 ? 2 : 7;
    const bool mine = (h & 1) ? t >= 2 : t < 2;
    qml[h] = mine ? qlo[hf] : 0u;
    qmh[h] = mine ? qhi[hf] : 0u;
    float a[4] = {0.f, 0.f, 0.f, 0.f}, c[4] = {0.f, 0.f, 0.f, 0.f};
    mma16816(a, qlo[f], qhi[f], qlo[f + 1], qhi[f + 1], klo[f], klo[f + 1]);
    mma16816(c, qlo[f], qhi[f], qlo[f + 1], qhi[f + 1], khi[f], khi[f + 1]);
    mma1688(a, qml[h], qmh[h], klo[hf]);
    mma1688(c, qml[h], qmh[h], khi[hf]);
    slo[h][0] = a[0];
    slo[h][1] = a[1];
    shi[h][0] = lg[h & 1][0] = far0 ? a[2] : c[2];
    shi[h][1] = lg[h & 1][1] = far1 ? a[3] : c[3];
    if (!ATT_MERGE && (h & 1)) softmax_two(lg, phi[h - 1], phi[h]);
  }
  TSIF(par == 0 && w == 1, 65);
  if (ATT_GATE == 3 && lane == 0) mbar_arrive(sb + OFF_BAR + 8 * B_ATT2 + (phi[3] & zero));
  wg_sync(1 + par);
  TSIF(par == 0 && w == 1, 66);
  const bool nohist = (w == 0) && (b < 8);
  const uint4* hp = g_halo + ((b - 8) * 2 + par) * 224 + lane;
  uint32_t tg[7];
  if (w > 0) {
    const uint4 v0 = lds128(xa + (w - 1) * 2560), v1 = lds128(xa + (w - 1) * 2560 + 512), v2 = lds128(xa + (w - 1) * 2560 + 1024);
    const uint4 v3 = lds128(xa + (w - 1) * 2560 + 1536), v4 = lds128(xa + (w - 1) * 2560 + 2048);
    kpv[0] = v0.x; kpv[1] = v0.y; kpv[2] = v0.z; kpv[3] = v0.w; kpv[4] = v1.x; kpv[5] = v1.y; kpv[6] = v1.z; kpv[7] = v1.w;
    kpv[8] = v2.x; kpv[9] = v2.y; vpv[0] = v2.z; vpv[1] = v2.w; vpv[2] = v3.x; vpv[3] = v3.y; vpv[4] = v3.z; vpv[5] = v3.w;
    vpv[6] = v4.x; vpv[7] = v4.y; vpv[8] = v4.z; vpv[9] = v4.w;
  } else if (nohist) {
#pragma unroll
    for (int j = 0; j < 10; j++) kpv[j] = vpv[j] = 0u;
  } else {
    TSIF(par == 0, 77);
    halo_read(kpv, vpv, tg, hp);
  }
  if (w == 0 && !nohist) {
    int spins = 0;
    while (true) {
      bool ok = true;
#pragma unroll
      for (int j = 0; j < 7; j++) ok = ok && tg[j] == tag;
      if (__all_sync(0xffffffffu, ok) || ++spins > SPIN_LIMIT) break;
      halo_read(kpv, vpv, tg, hp);
    }
    TSIF(par == 0, 79);
  }
#pragma unroll
  for (int h = 0; h < 4; h++) {
    const int f = h == 0 ? 0 : h == 1 ? 3 : h == 2 ? 5 : 8, hf = h < 2 ? 2 : 7;
    float a[4] = {0.f, 0.f, 0.f, 0.f};
    mma16816(a, qlo[f], qhi[f], qlo[f + 1], qhi[f + 1], kpv[f], kpv[f + 1]);
    mma1688(a, qml[h], qmh[h], kpv[hf]);
    const float ninf = __int_as_float(0xff800000);
    lg[h & 1][0] = far0 ? (nohist ? ninf : a[0]) : slo[h][0];
    lg[h & 1][1] = far1 ? (nohist ? ninf : a[1]) : slo[h][1];
    if (h & 1) {
      softmax_two(lg, plo[h - 1], plo[h]);
      if (ATT_MERGE) {
        const float lh[2][2] = {{shi[h - 1][0], shi[h - 1][1]}, {shi[h][0], shi[h][1]}};
        softmax_two(lh, phi[h - 1], phi[h]);
      }
    }
  }
  TSIF(par == 0 && w <= 1, 67 + w);
  if (ATT_GATE == 2 && lane == 0) mbar_arrive(sb + OFF_BAR + 8 * B_ATT2 + (plo[3] & zero));
  uint32_t ov[20];
#pragma unroll
  for (int hp = 0; hp < 2; hp++) {
    const int hf = hp ? 7 : 2;
    float sh[4] = {0.f, 0.f, 0.f, 0.f}, i0 = 0.f, i1 = 0.f;
#pragma unroll
    for (int e = 0; e < 2; e++) {
      const int h = 2 * hp + e, f = h == 0 ? 0 : h == 1 ? 3 : h == 2 ? 5 : 8;
      const uint32_t a0 = plo[h] & mfar, a2 = plo[h] & ~mfar, a3 = phi[h] & mfar, c1 = phi[h] & ~mfar;
      float sum[4] = {0.f, 0.f, 0.f, 0.f};
      mma1688(sum, plo[h], phi[h], 0x3F803F80u);
      const float r0 = rcp(sum[0]), r1 = rcp(sum[2]);
#pragma unroll
      for (int j = f; j < f + 2; j++) {
        float o[4] = {0.f, 0.f, 0.f, 0.f};
        mma16816(o, a0, 0u, a2, a3, vpv[j], vlo[j]);
        mma1688(o, 0u, c1, vhi[j]);
        ov[2 * j] = pack2(o[0] * r0, o[1] * r0);
        ov[2 * j + 1] = pack2(o[2] * r1, o[3] * r1);
      }
      const bool mine = e ? g >= 4 : g < 4;
      mma16816(sh, a0, 0u, a2, a3, mine ? vpv[hf] : 0u, mine ? vlo[hf] : 0u);
      mma1688(sh, 0u, c1, mine ? vhi[hf] : 0u);
      if (e == 0 || t >= 2) {
        i0 = r0;
        i1 = r1;
      }
    }
    ov[2 * hf] = pack2(sh[0] * i0, sh[1] * i0);
    ov[2 * hf + 1] = pack2(sh[2] * i1, sh[3] * i1);
  }
  if (ATT_GATE == 4 && lane == 0) mbar_arrive(sb + OFF_BAR + 8 * B_ATT2 + (ov[19] & zero));
  TS(32 + 4 * par + w);
  mbar_wait(sb + OFF_BAR + 8 * B_P1, 0);
  const uint32_t oa = sb + OFF_OA + (lane >> 4) * 2048 + (32 * w + 2 * (lane & 15) + par) * 16;
#pragma unroll
  for (int j = 0; j < 5; j++) stsm4(oa + 4096 * j, ov + 4 * j);
  TSIF(par == 0 && w == 0, 120);
  fence_async_smem();
  TSIF(par == 0 && w == 0, 121);
  __syncwarp();
  if (lane == 0) mbar_arrive(sb + OFF_BAR + 8 * B_ATTN);
  TSM(w == 0 || w == 2, 122 + par + (w == 2 ? 3 : 0));
}

struct Maps {
  CUtensorMap x, wm, wt, k, v, y, wo, qm, qt, om, ot, u;
};

__device__ __forceinline__ void load_stage(uint32_t sb, int kb, int b, const Maps& m) {
  const uint32_t st = sb + (kb & 3) * STAGE_BYTES, bar = sb + OFF_BAR + 8 * (B_FULL1 + (kb & 3));
  const int r = b >> 3, hg = b & 7, slab = kb - KV_KB;
  const bool kv = slab >= 0 && slab < 5;
  const uint32_t kbar = sb + OFF_BAR + 8 * (B_KV + slab), dst = sb + OFF_KVS + slab * KVS_BYTES;
  mbar_expect_tx(bar, STAGE_BYTES);
  if (kv) mbar_expect_tx(kbar, KVS_BYTES);
  tma_3d(st, &m.x, 64 * kb, 64 * r, 0, bar);
  if (kv && KV_MIX) tma_3d(dst, &m.k, 0, 32 * (b >> 1) - 3, 2 * slab + (b & 1), kbar);
  tma_3d(st + ST_W, &m.wm, 80 * hg + (tail_first(hg) ? 16 : 0), 64 * kb, 0, bar);
  if (kv && KV_MIX) tma_3d(dst + KVS_V, &m.v, 0, 32 * (b >> 1), 2 * slab + (b & 1), kbar);
  tma_3d(st + ST_WT, &m.wt, 80 * hg + (tail_first(hg) ? 0 : 64), 64 * kb, 0, bar);
  if (kv && !KV_MIX) tma_3d(dst, &m.k, 0, 32 * (b >> 1) - 3, 2 * slab + (b & 1), kbar);
  if (kv && !KV_MIX) tma_3d(dst + KVS_V, &m.v, 0, 32 * (b >> 1), 2 * slab + (b & 1), kbar);
}

__global__ void __launch_bounds__(NTHR, 1) fused_kernel(const __grid_constant__ Maps m, const Params p) {
  extern __shared__ __align__(1024) uint8_t smem[];
  const uint32_t sb = (uint32_t)__cvta_generic_to_shared(smem);
  const uint32_t bars = sb + OFF_BAR;
  const int tid = threadIdx.x, lane = tid & 31;
  int b = blockIdx.x;
  if (BMAP == 1) b = (((b & 63) >> 3) * 2 + (b & 1)) * 8 + (((b < 64 ? 0x6521 : 0x7430) >> (4 * ((b >> 1) & 3))) & 7);
  if (BMAP == 2) b = ((b & 63) >> 2) * 8 + (((b < 64 ? 0x6521 : 0x7430) >> (4 * (b & 3))) & 7);
  if (BMAP == 3) b = (((b & 63) >> 3) * 2 + (b & 1)) * 8 + (((b < 64 ? 0x7430 : 0x6521) >> (4 * ((b >> 1) & 3))) & 7);
  if (BMAP == 4) b = (((b >> 4) * 2 + (b & 1)) * 8) + ((b >> 1) & 7);
  if (BMAP == 5) b = 127 - b;
  const int r = b >> 3, hg = b & 7;

  if (tid == T_ISSUE) {
    TSM(true, 0);
#pragma unroll
    for (int i = 0; i < 4; i++) mbar_init(bars + 8 * (B_FULL1 + i), 1);
#pragma unroll
    for (int i = 0; i < 3; i++) mbar_init(bars + 8 * (B_KV + i), 1);
    fence_async_smem();
#pragma unroll 1
    for (int kb = 0; kb <= PRE2; kb++) load_stage(sb, kb, b, m);
  } else if (tid >= T_PF && tid < T_PF + 12) {
    tm_prefetch(&m.x + (tid - T_PF));
  } else if (tid == T_INIT) {
#pragma unroll
    for (int i = 0; i < 4; i++) mbar_init(bars + 8 * (B_EMPTY1 + i), 8);
#pragma unroll
    for (int i = 0; i < 8; i++) mbar_init(bars + 8 * (B_FULL2 + i), 1);
#pragma unroll
    for (int i = 0; i < 4; i++) mbar_init(bars + 8 * (B_EMPTY2 + i), 8);
#pragma unroll
    for (int i = 0; i < 4; i++) mbar_init(bars + 8 * (B_U + i), 1);
    mbar_init(bars + 8 * B_HA, 4);
    mbar_init(bars + 8 * B_GATE, 4);
    mbar_init(bars + 8 * B_HB, 1);
    mbar_init(bars + 8 * B_KVD, 4);
    mbar_init(bars + 8 * B_QF, 1);
    mbar_init(bars + 8 * B_ATTN, 8);
    mbar_init(bars + 8 * B_ATT2, 8);
    mbar_init(bars + 8 * B_P1, 8);
    mbar_init(bars + 8 * B_C34, 1);
#pragma unroll
    for (int i = 0; i < 5; i++) mbar_init(bars + 8 * (B_YST + i), 4);
#pragma unroll
    for (int i = 0; i < 5; i++) mbar_init(bars + 8 * (B_US + i), 4);
    mbar_init(bars + 8 * B_YSIG, 1);
    mbar_init(bars + 8 * B_YFULL, 1);
    mbar_init(bars + 8 * B_EPOCH, 1);
    mbar_init(bars + 8 * B_PREP, 4);
    mbar_init(bars + 8 * B_USIG, 1);
    mbar_init(bars + 8 * B_WST, 1);
#pragma unroll
    for (int i = 3; i < 5; i++) mbar_init(bars + 8 * (B_KV + i), 1);
    mbar_init(bars + 8 * B_E3, 8);
    mbar_init(bars + 8 * B_LAST, 1);
    mbar_init(bars + 8 * B_OSIG, 1);
    mbar_init(bars + 8 * B_WOP, 1);
    fence_async_smem();
  }
  const int warp = __shfl_sync(0xffffffffu, tid >> 5, 0), wg = warp >> 2, w = warp & 3;
  __syncthreads();

  if (wg == 3) {
    asm volatile("setmaxnreg.dec.sync.aligned.u32 56;");
    if (w == 0) {
      if (lane == 0) {
#pragma unroll 1
        for (int kb = 1 + PRE2; kb < 10; kb++) {
          if (kb >= 4) mbar_wait(bars + 8 * (kb == 7 ? B_E3 : B_EMPTY1 + (kb & 3)), (kb >> 3) & 1);
          TSIF(kb >= 4, 44 + kb);
          load_stage(sb, kb, b, m);
          TSIF(kb == 3, 60);
          if (kb == TRIG_KB) mbar_arrive(bars + 8 * B_LAST);
        }
        mbar_wait(bars + 8 * B_WOP, 0);
        mbar_wait(bars + 8 * WL_TRIG, 0);
        mbar_wait(bars + 8 * B_EPOCH, 0);
        flag_wait(g_cnt + C_W + 32 * hg, (lds32(sb + OFF_EPOCH) + 1) * 16);
        TS(30);
#pragma unroll 1
        for (int j = 0; j < 8; j++) {
          if (j >= 6) mbar_wait(bars + 8 * (B_EMPTY2 + j - 6), 0);
          if (j == 4) mbar_wait(bars + 8 * B_ATTN, 0);
          TSIF(j >= 6, 100 + j);
          if (RF_GATE && j == 6) mbar_wait(bars + 8 * B_YSIG, 0);
          mbar_expect_tx(bars + 8 * (B_FULL2 + j), j == 0 ? WO_BYTES : j == 5 ? O_BYTES + WO_BYTES + 512 : O_BYTES + WO_BYTES);
          bulk_load(sb + off_w(j), g_WO + (hg * 8 + step_src(hg, j)) * 800, WO_BYTES, bars + 8 * (B_FULL2 + j));
        }
        mbar_wait(bars + 8 * (B_EMPTY2 + 3), 0);
        mbar_expect_tx(bars + 8 * B_QF, O_BYTES);
        tma_2d(sb + OFF_QS, &m.qm, 80 * hg, 128 * r, bars + 8 * B_QF);
        tma_2d(sb + OFF_QT, &m.qt, 80 * hg + 64, 128 * r, bars + 8 * B_QF);
      }
    } else if (w == 1) {
      unsigned epoch = 0;
      if (lane == 0) {
        epoch = atomicAdd(g_cnt + C_LAUNCH, 1u) / NCTA;
        asm volatile("st.shared.u32 [%0], %1;" ::"r"(sb + OFF_EPOCH), "r"(epoch) : "memory");
        mbar_arrive(bars + 8 * B_EPOCH);
        mbar_wait(bars + 8 * B_KVD, 0);
        mbar_expect_tx(bars + 8 * B_HB, 5 * 4096);
#pragma unroll 1
        for (int c = 0; c < 5; c++) {
          if (c == 3) mbar_wait(bars + 8 * B_S3, 0);
          bulk_load(sb + off_ch(c) + U_BYTES, p.ssm_k + (5 * b + c) * SEQ, 4096, bars + 8 * B_HB);
        }
#pragma unroll
        for (int c = 0; c < 4; c++) mbar_expect_tx(bars + 8 * (B_U + c), c < 3 ? U_BYTES : 2 * U_BYTES);
        const uint4* usrc = g_U + 5 * b * U_PITCH;
        mbar_wait(bars + 8 * B_USIG, 0);
        flag_wait(g_cnt + C_PREP + 32 * (b & 15), (epoch + 1) * NCTA);
        TS(23);
#pragma unroll
        for (int c = 0; c < 5; c++) {
          if (c == 3 && U_TRIM) mbar_wait(bars + 8 * (B_U + 2), 0);
          bulk_load(sb + off_ch(c), usrc + c * U_PITCH, U_BYTES, bars + 8 * (B_U + (c < 3 ? c : 3)));
          TSIF(c == 0 || c == 4, 116 + (c >> 2));
        }
      }
      epoch = __shfl_sync(0xffffffffu, epoch, 0);
      if (lane < 8) {
        const int src = (b & ~7) | step_src(hg, lane);
        mbar_wait(bars + 8 * OP_TRIG, 0);
        TS(20);
        bool seen = false;
#pragma unroll 1
        for (int spins = 0; spins < SPIN_LIMIT; spins++) {
          const bool now = !seen && (int)(flag_read(g_cnt + C_O + 32 * src) - (epoch + 1)) >= 0;
          if (now && lane >= 1 && lane < 4) bulk_load(sb + off_o(lane), g_O + src * 1280, O_BYTES, bars + 8 * (B_FULL2 + lane));
          seen = seen || now;
          if (__all_sync(0xff, seen)) break;
        }
        TS(21);
        if (lane == 5) bulk_load(sb + OFF_GATE, g_gate + 128 * r, 512, bars + 8 * (B_FULL2 + 5));
#pragma unroll 1
        for (int j = 4; j < 8; j++) {
          if (lane == j) {
            mbar_wait(bars + 8 * (j < 6 ? B_C34 : B_EMPTY2 + j - 6), 0);
            if (RF_GATE && j == 6) mbar_wait(bars + 8 * B_YSIG, 0);
            bulk_load(sb + off_o(j), g_O + src * 1280, O_BYTES, bars + 8 * (B_FULL2 + j));
          }
          __syncwarp(0xff);
        }
        TS(22);
      }
    } else if (w == 2) {
      mbar_wait(bars + 8 * B_PREP, 0);
      flag_signal(g_cnt + C_PREP, 16, lane);
      TS(25);
      if (lane == 0) mbar_arrive(bars + 8 * B_USIG);
      mbar_wait(bars + 8 * B_GATE, 0);
      if (((NOMB & 1) || O_RB) && lane == 0) asm volatile("fence.release.gpu;" ::: "memory");
      mbar_wait(bars + 8 * B_ATTN, 0);
      if (lane == 0) {
        if (O_DEFER) mbar_wait(bars + 8 * (B_U + 3), 0);
        asm volatile("cp.async.bulk.global.shared::cta.bulk_group [%0], [%1], 20480;\ncp.async.bulk.commit_group;"
                     ::"l"(g_O + b * 1280), "r"(sb + OFF_OA) : "memory");
        if (O_RB) asm volatile("cp.async.bulk.wait_group.read 0;" ::: "memory");
        else asm volatile("cp.async.bulk.wait_group 0;\nfence.proxy.async.global;" ::: "memory");
      }
      TS(74);
      if (O_RB) {
        __syncwarp();
        unsigned v[5];
#pragma unroll
        for (int c = 0; c < 5; c++) v[c] = flag_read(reinterpret_cast<const unsigned*>(g_O + b * 1280 + 256 * c + 8 * lane + 7));
        const unsigned dep = __reduce_or_sync(0xffffffffu, (v[0] ^ v[1] ^ v[2] ^ v[3] ^ v[4]) & p.zero);
        if (lane == 0) flag_bump(g_cnt + C_O + 32 * b + dep);
      } else if (!(NOMB & 1)) flag_signal(g_cnt + C_O + 32 * b, 1, lane);
      else if (lane == 0) flag_bump(g_cnt + C_O + 32 * b);
      TS(26);
      if (lane == 0) mbar_arrive(bars + 8 * B_OSIG);

    } else {
      if (lane == 0) {
        uint4* dst = g_WO + (hg * 8 + (r >> 1)) * 800 + (r & 1) * 80;
        mbar_wait(bars + 8 * B_P1, 0);
        mbar_wait(bars + 8 * WB_TRIG, 0);
        mbar_expect_tx(bars + 8 * B_WST, WO_BYTES / 2);
        tma_3d(sb + OFF_WS, &m.wo, 0, 40 * r, 5 * hg, bars + 8 * B_WST);
        mbar_wait(bars + 8 * B_WST, 0);
        mbar_wait(bars + 8 * WO_TRIG, 0);
#pragma unroll 1
        for (int n = 0; n < 5; n++)
          asm volatile("cp.async.bulk.global.shared::cta.bulk_group [%0], [%1], 1280;" ::"l"(dst + 160 * n), "r"(sb + OFF_WS + 1280 * n) : "memory");
        asm volatile("cp.async.bulk.commit_group;\ncp.async.bulk.wait_group 0;\nfence.proxy.async.global;" ::: "memory");
        if (!(NOMB & 4)) asm volatile("fence.release.gpu;" ::: "memory");
        flag_bump(g_cnt + C_W + 32 * hg);
        mbar_arrive(bars + 8 * B_WOP);
        TS(71);
#pragma unroll 1
        for (int c = 0; c < 5; c++) {
          mbar_wait(bars + 8 * (B_YST + c), 0);
          asm volatile("cp.async.bulk.global.shared::cta.bulk_group [%0], [%1], 4096;\ncp.async.bulk.commit_group;"
                       ::"l"(g_Y + (5 * b + c) * Y_PITCH), "r"(sb + off_ch(c)) : "memory");
          if (c == 2) {
            asm volatile("cp.async.bulk.wait_group.read 0;" ::: "memory");
            mbar_arrive(bars + 8 * B_C34);
          }
        }
        if (Y_RB) asm volatile("cp.async.bulk.wait_group.read 0;" ::: "memory");
        else asm volatile("cp.async.bulk.wait_group 0;\nfence.proxy.async.global;" ::: "memory");
        TS(75);
      }
      unsigned dep = 0;
      if (Y_RB) {
        __syncwarp();
        unsigned v[5];
#pragma unroll
        for (int c = 0; c < 5; c++) v[c] = flag_read(reinterpret_cast<const unsigned*>(g_Y + (5 * b + c) * Y_PITCH + 8 * lane + 7));
        dep = __reduce_or_sync(0xffffffffu, (v[0] ^ v[1] ^ v[2] ^ v[3] ^ v[4]) & p.zero);
      }
      if (lane == 0) {
        if (!Y_RB && !(NOMB & 2)) asm volatile("fence.release.gpu;" ::: "memory");
        flag_bump(g_cnt + C_Y + 32 * (b >> 4) + dep);
        TS(27);
        mbar_arrive(bars + 8 * B_YSIG);
        mbar_expect_tx(bars + 8 * B_YFULL, 20480);
        flag_wait(g_cnt + C_Y + 32 * hg, (lds32(sb + OFF_EPOCH) + 1) * 16);
        TS(24);
        tma_2d(sb + OFF_YT, &m.y, 128 * r, 80 * hg, bars + 8 * B_YFULL);
        tma_2d(sb + OFF_YT + 10240, &m.y, 128 * r + 64, 80 * hg, bars + 8 * B_YFULL);
      }
    }
  } else {
    asm volatile("setmaxnreg.inc.sync.aligned.u32 152;");
    if (wg < 2) {
      float acc[120];
#pragma unroll
      for (int i = 0; i < 120; i++) acc[i] = 0.f;
      const uint32_t da = desc_lo(sb + wg * 8192, 16), db = desc_lo(sb + ST_W, 8192), dc = desc_lo(sb + ST_WT, 2048);
      if (PW1) pin<120>(acc);
      if (PW1 == 2) mbar_wait(bars + 8 * B_FULL1, 0);
#pragma unroll 1
      for (int kb = 0; kb < 10; kb++) {
        mbar_wait(bars + 8 * (B_FULL1 + (kb & 3)), (kb >> 2) & 1);
        const uint32_t so = (kb & 3) * (STAGE_BYTES >> 4);
        wg_fence();
#pragma unroll
        for (int k = 0; k < 4; k++) {
          WgSST<192>::mma<HI_SW128, HI_SW128>(acc, da + so + 2 * k, db + so + 128 * k, 1);
          WgSST<48>::mma<HI_SW128, HI_SW32>(acc + 96, da + so + 2 * k, dc + so + 32 * k, 1);
        }
        wg_commit();
        wg_wait<1>();
        if (kb > 0 && lane == 0) mbar_arrive(bars + 8 * (kb == 4 ? B_E3 : B_EMPTY1 + ((kb - 1) & 3)));
      }
      mbar_wait(bars + 8 * B_EPOCH, 0);
      const uint32_t tag = lds32(sb + OFF_EPOCH) + 1;
      mbar_wait(bars + 8 * B_S3, 0);
      wg_wait<0>();
      pin<120>(acc);
      if (lane == 0) mbar_arrive(bars + 8 * B_P1);
      TSM(w == 0, 3 + wg);
      attention(acc, sb, b, wg, w, lane, tag, p.zero);
    } else {
      const int tw = tid & 127, chl = 64 * (b & 1) + 8 * w + (lane >> 2);
      uint4* up = g_U + chl * U_PITCH + ((4 * (b >> 1) + (lane & 3)) ^ ((b >> 2) & 1));
      uint2 sw[10];
      uint32_t dv = 0;
      if (lane < 5) dv = __ldg(reinterpret_cast<const unsigned short*>(p.ssm_D) + 5 * b + lane);
#pragma unroll
      for (int i = 0; i < 10; i++) sw[i] = ldg64(reinterpret_cast<const uint2*>(p.shift_k) + chl + 128 * (i >> 1) + 32 * (i & 1));
      uint32_t tab[12];
      uint32_t tt[2];
      fft_tables(tab, tw);
      fft_twiddles(tt, tw);
      uint4 res[10];
#pragma unroll
      for (int i = 0; i < 10; i++) res[i] = make_uint4(0, 0, 0, 0);
#pragma unroll 1
      for (int slab = 0; slab < 5; slab++) {
#pragma unroll
        for (int i = 0; i < 8; i++) res[i] = res[i + 2];
        prep_slab(res + 8, sw, sb, slab, w, lane);
        TSIF(w == 0, 99 + 4 * slab);
#pragma unroll
        for (int i = 0; i < 8; i++) sw[i] = sw[i + 2];
      }
      TSIF(w == 0, 28);
      __syncwarp();
      if (lane == 0) mbar_arrive(bars + 8 * B_KVD + ((res[8].x ^ res[9].x) & p.zero));
      mbar_wait(bars + 8 * B_KVD, 0);
      fft_tables_store(tab, sb, tw);
      mbar_wait(bars + 8 * B_LAST, 0);
#pragma unroll
      for (int i = 0; i < 10; i++) up[(128 * (i >> 1) + 32 * (i & 1)) * U_PITCH] = res[i];
      __syncwarp();
      if (lane == 0) mbar_arrive(bars + 8 * B_PREP);
      TSIF(w == 0 && !U_TMA, 5);
      mbar_wait(bars + 8 * (G_AFTER ? B_USIG : B_LAST), 0);
      prep_gate(p, b, w, lane);
      __syncwarp();
      if (lane == 0) mbar_arrive(bars + 8 * B_GATE);
      TSIF(w == 0, 72);
      mbar_wait(bars + 8 * B_HB, 0);
      TSIF(w == 0, 2);
      const uint32_t ha = sb + U_BYTES + ((tw >> 3) * 16 + 8 + (tw & 7)) * 16;
      uint4 hv[5];
#pragma unroll
      for (int c = 0; c < 5; c++) hv[c] = lds128(ha + off_ch(c));
      __syncwarp();
#pragma unroll
      for (int c = 0; c < 5; c++) sts128((ha ^ 16) + off_ch(c), hv[c].x, hv[c].y, hv[c].z, hv[c].w);
      asm volatile("st.shared.v2.u32 [%0], {%1, %2};" ::"r"(sb + OFF_TT + 8 * tw), "r"(tt[0]), "r"(tt[1]) : "memory");
      if (tw < 5) asm volatile("st.shared.f32 [%0], %1;" ::"r"(sb + OFF_D + 4 * tw), "f"(bf_lo(dv) * 0.125f) : "memory");
      fence_async_smem();
      __syncwarp();
      if (lane == 0) mbar_arrive(bars + 8 * B_HA);
      TSIF(w == 0, 6);
    }

    FftConst fc;
    TSM(w == 0 && wg == 0, 104);
    mbar_wait(bars + 8 * B_HA, 0);
    fft_matrices(fc, sb, w, lane);
    TSM(w == 0 && wg == 0, 105);
    TSM(w == 0 && wg == 2, 124);
#pragma unroll 1
    for (uint32_t tasks = wg == 0 ? TASK0 : wg == 1 ? TASK1 : TASK2; tasks; tasks >>= 4) {
      const int c = (tasks & 7) - 1;
      conv_channel(fc, sb, c, wg, w, lane);
      if (lane == 0) mbar_arrive(bars + 8 * (B_YST + c));
      TSM(w == 0, 10 + c);
    }

    if (wg < 2) {
      const int g = lane >> 2;
      float acc[40];
#pragma unroll
      for (int i = 0; i < 40; i++) acc[i] = 0.f;
      const uint32_t da = desc_lo(sb + wg * 1024, 2048), db = desc_lo(sb, 2560);
      if (!WO_FAST) mbar_wait(bars + 8 * B_ATTN, 0);
      mbar_wait(bars + 8 * (B_YST + 3), 0);
      mbar_wait(bars + 8 * (B_YST + 4), 0);
      if (PW2 && !WO_FAST) mbar_wait(bars + 8 * B_FULL2, 0);
      TSM(w == 0, 15 + wg);
#pragma unroll 1
      for (int j = 0; j < 8; j++) {
        mbar_wait(bars + 8 * (B_FULL2 + j), 0);
        const uint32_t oa = da + (off_o(j) >> 4), ob = db + (off_w(j) >> 4);
        wg_fence();
#pragma unroll
        for (int k = 0; k < 5; k++) WgSST<80>::mma<HI_NONE, HI_SW32>(acc, oa + 256 * k, ob + 32 * k, 1);
        wg_commit();
        wg_wait<1>();
        if (j >= 1 && j <= 4 && lane == 0) mbar_arrive(bars + 8 * (B_EMPTY2 + j - 1));
      }
      TSIF(w == 0 && wg == 0, 113);
      const int tr = 64 * wg + 16 * w + (lane & 15);
      const uint32_t fm = sb + OFF_QS + tr * 128, fx = (lane >> 4) ^ (tr & 7);
      const uint32_t ft = sb + OFF_QT + tr * 32 + (((lane >> 4) ^ (tr >> 2)) & 1) * 16;
      const float g0 = __uint_as_float(lds32(sb + OFF_GATE + (64 * wg + 16 * w + g) * 4));
      const float g1 = __uint_as_float(lds32(sb + OFF_GATE + (64 * wg + 16 * w + 8 + g) * 4));
      const uint32_t ga = pack2(g0, g0), gb = pack2(g1, g1);
      const uint32_t na = pack2(1.f - g0, 1.f - g0), nb = pack2(1.f - g1, 1.f - g1);

      uint32_t qf[20];
      mbar_wait(bars + 8 * B_QF, 0);
#pragma unroll
      for (int j = 0; j < 5; j++) ldsm4(qf + 4 * j, j < 4 ? fm + ((fx ^ (2 * j)) << 4) : ft);
      if (FUSE_MIX) {
#pragma unroll
        for (int i = 0; i < 20; i++) {
          qf[i] = bmul((i & 1) ? gb : ga, qf[i]);
          asm volatile("" : "+r"(qf[i]));
        }
      }
      wg_wait<0>();
      pin<40>(acc);
      TSM(w == 0, 17 + wg);
      uint32_t pb[20];
#pragma unroll
      for (int j = 0; j < 10; j++) {
        pb[2 * j] = bmul(na, pack2(acc[4 * j], acc[4 * j + 1]));
        pb[2 * j + 1] = bmul(nb, pack2(acc[4 * j + 2], acc[4 * j + 3]));
        asm volatile("" : "+r"(pb[2 * j]), "+r"(pb[2 * j + 1]));
      }
      const uint32_t ya = sb + OFF_YT + wg * 10240 + ((lane >> 4) * 8 + (lane & 7)) * 128 +
                          (((2 * w + (((lane >> 3) & 1) ^ wg)) ^ (lane & 7)) << 4);
      mbar_wait(bars + 8 * B_YFULL, 0);
      TSM(w == 0 && wg == 0, 19);
#pragma unroll
      for (int j = 0; j < 5; j++) {
        uint32_t y[4];
        ldsm4t(y, ya + 2048 * j);
#pragma unroll
        for (int i = 0; i < 4; i++)
          qf[4 * j + i] = FUSE_MIX ? bfma(qf[4 * j + i], y[i], pb[4 * j + i]) : badd(bmul((i & 1) ? gb : ga, bmul(qf[4 * j + i], y[i])), pb[4 * j + i]);
      }
#pragma unroll
      for (int j = 0; j < 5; j++) stsm4(j < 4 ? fm + ((fx ^ (2 * j)) << 4) : ft, qf + 4 * j);
      fence_async_smem();
      __syncwarp();
      if (lane == 0) {
        const int row = 64 * wg + 16 * w;
        asm volatile("cp.async.bulk.tensor.2d.global.shared::cta.bulk_group [%0, {%2, %3}], [%1];"
                     ::"l"(&m.om), "r"(sb + OFF_QS + row * 128), "r"(80 * hg), "r"(128 * r + row) : "memory");
        asm volatile("cp.async.bulk.tensor.2d.global.shared::cta.bulk_group [%0, {%2, %3}], [%1];"
                     ::"l"(&m.ot), "r"(sb + OFF_QT + row * 32), "r"(80 * hg + 64), "r"(128 * r + row) : "memory");
        asm volatile("cp.async.bulk.commit_group;\ncp.async.bulk.wait_group.read 0;" ::: "memory");
      }
      TSM(true, 40 + 4 * wg + w);
      if (ENDBAR) asm volatile("bar.sync 15, 256;" ::: "memory");
    }
  }
}

typedef CUresult (*EncodeFn)(CUtensorMap*, CUtensorMapDataType, cuuint32_t, void*, const cuuint64_t*, const cuuint64_t*,
                             const cuuint32_t*, const cuuint32_t*, CUtensorMapInterleave, CUtensorMapSwizzle,
                             CUtensorMapL2promotion, CUtensorMapFloatOOBfill);

void encode(EncodeFn fn, CUtensorMap* tm, const void* base, int rank, const cuuint64_t* dims, const cuuint64_t* strides,
            const cuuint32_t* box, CUtensorMapSwizzle swz) {
  const cuuint32_t ones[3] = {1, 1, 1};
  fn(tm, CU_TENSOR_MAP_DATA_TYPE_BFLOAT16, rank, const_cast<void*>(base), dims, strides, box, ones,
     CU_TENSOR_MAP_INTERLEAVE_NONE, swz, CU_TENSOR_MAP_L2_PROMOTION_L2_128B, CU_TENSOR_MAP_FLOAT_OOB_FILL_NONE);
}

}

extern "C" void kernel_launch(void* const* d_in, const int* in_sizes, int n_in, void* d_out, int out_size) {
  (void)in_sizes; (void)n_in; (void)out_size;
  Params p;
  p.q = (const __nv_bfloat16*)d_in[0];
  p.k = (const __nv_bfloat16*)d_in[1];
  p.v = (const __nv_bfloat16*)d_in[2];
  p.shift_k = (const __nv_bfloat16*)d_in[3];
  p.ssm_k = (const __nv_bfloat16*)d_in[4];
  p.ssm_D = (const __nv_bfloat16*)d_in[5];
  p.wqkv = (const __nv_bfloat16*)d_in[7];
  p.wo = (const __nv_bfloat16*)d_in[8];
  p.gate_w = (const __nv_bfloat16*)d_in[9];
  p.out = (__nv_bfloat16*)d_out;
  p.zero = 0;

  static EncodeFn fn = nullptr;
  static void *yaddr = nullptr, *uaddr = nullptr;
  if (!fn) {
    cudaDriverEntryPointQueryResult qr;
    void* f = nullptr;
    cudaGetDriverEntryPoint("cuTensorMapEncodeTiled", &f, cudaEnableDefault, &qr);
    fn = (EncodeFn)f;
    cudaGetSymbolAddress(&yaddr, g_Y);
    cudaGetSymbolAddress(&uaddr, g_U);
    cudaFuncSetAttribute(fused_kernel, cudaFuncAttributeMaxDynamicSharedMemorySize, SMEM_BYTES);
  }
  Maps m;
  {
    const cuuint64_t dims[3] = {640, 1024, 2}, st[2] = {2560, 1280};
    const cuuint32_t box[3] = {64, 64, 2};
    encode(fn, &m.x, p.q, 3, dims, st, box, CU_TENSOR_MAP_SWIZZLE_128B);
  }
  {
    const cuuint64_t dims[3] = {640, 640, 3}, st[2] = {3840, 1280};
    const cuuint32_t box[3] = {64, 64, 3}, boxt[3] = {16, 64, 3};
    encode(fn, &m.wm, p.wqkv, 3, dims, st, box, CU_TENSOR_MAP_SWIZZLE_128B);
    encode(fn, &m.wt, p.wqkv, 3, dims, st, boxt, CU_TENSOR_MAP_SWIZZLE_32B);
  }
  {
    const cuuint64_t dims[3] = {64, 2048, 10}, st[2] = {1280, 128};
    const cuuint32_t boxk[3] = {64, 35, 1}, boxv[3] = {64, 32, 1};
    encode(fn, &m.k, p.k, 3, dims, st, boxk, CU_TENSOR_MAP_SWIZZLE_128B);
    encode(fn, &m.v, p.v, 3, dims, st, boxv, CU_TENSOR_MAP_SWIZZLE_128B);
  }
  {
    const cuuint64_t dims[3] = {16, 640, 40}, st[2] = {1280, 32};
    const cuuint32_t box[3] = {16, 40, 5};
    encode(fn, &m.wo, p.wo, 3, dims, st, box, CU_TENSOR_MAP_SWIZZLE_32B);
  }
  {
    const cuuint64_t dims[2] = {2048, 640}, st[1] = {Y_PITCH * 16};
    const cuuint32_t box[2] = {64, 80};
    encode(fn, &m.y, yaddr, 2, dims, st, box, CU_TENSOR_MAP_SWIZZLE_128B);
    const cuuint64_t stu[1] = {U_PITCH * 16};
    const cuuint32_t boxu[2] = {32, 64};
    encode(fn, &m.u, uaddr, 2, dims, stu, boxu, CU_TENSOR_MAP_SWIZZLE_NONE);
  }
  {
    const cuuint64_t dims[2] = {640, 2048}, st[1] = {1280};
    const cuuint32_t bqm[2] = {64, 128}, bqt[2] = {16, 128}, bom[2] = {64, 16}, bot[2] = {16, 16};
    encode(fn, &m.qm, p.q, 2, dims, st, bqm, CU_TENSOR_MAP_SWIZZLE_128B);
    encode(fn, &m.qt, p.q, 2, dims, st, bqt, CU_TENSOR_MAP_SWIZZLE_32B);
    encode(fn, &m.om, p.out, 2, dims, st, bom, CU_TENSOR_MAP_SWIZZLE_128B);
    encode(fn, &m.ot, p.out, 2, dims, st, bot, CU_TENSOR_MAP_SWIZZLE_32B);
  }
  fused_kernel<<<NCTA, NTHR, SMEM_BYTES>>>(m, p);
}
```

```cpp
#include <cuda.h>
#include <cuda_bf16.h>
#include <cuda_runtime.h>
#include <stdint.h>

namespace {

constexpr int SEQ = 2048, DIM = 640, NCTA = 128, NTHR = 512;

#define TRIG_KB 9
#define KV_KB 2
#define DEV_EXIT 0
#define ATT_GATE 0
#define G_AFTER 0
#define FENCE_LO 0
#define FENCE_HI 0
#define PW1 2
#define PW2 1
#define ENDBAR 0
#define PAD_KB 0
#define Y_ALIAS 1
#define NOMB 0
#define SRC_ROT 0
#define WAIT_NS 0
#define WB_TRIG B_USIG
#define G_POS 0
#define TAILF 1
#define T_ISSUE 384
#define T_PF 416
#define T_INIT 448
#define ATT_MERGE 0
#define BMAP 1
#define PRE2 1
#define KV_MIX 0
#define O_DEFER 0
#define TASK0 0x52
#define TASK1 0x3
#define TASK2 0x41
#define HALO_FIRST 1
#define PREV_EARLY 0
#define Y_RB 2
#define O_RB 0
#define O_EAGER 1
#define OP_TRIG B_OSIG
#define FUSE_MIX 1
#define Q_EARLY 1
#define WO_FAST 0
#define U_TRIM 1
#define ACQ 0
#define U_TMA 0
#define U_GATE 0
#define RF_GATE 0
#define WO_TRIG B_WST
#define WL_TRIG B_WOP
#define WO_GATE 1

constexpr uint32_t STAGE_BYTES = 47104, ST_W = 16384, ST_WT = 40960;
constexpr uint32_t O_BYTES = 20480, WO_BYTES = 12800;
constexpr uint32_t OFF_OA = 0;
constexpr uint32_t OFF_QS = 3 * O_BYTES, OFF_QT = OFF_QS + 16384;
constexpr uint32_t OFF_WC = 81920;
constexpr uint32_t OFF_WA = 94720;
constexpr uint32_t OFF_GATE = 145920;
constexpr uint32_t OFF_TT = 146432;
constexpr uint32_t OFF_KVX = 148480;
constexpr uint32_t OFF_CH3 = 163840;
constexpr uint32_t CH_BYTES = 12288, U_BYTES = 4096;
constexpr uint32_t OFF_FT = 225280, OFF_GT = 229376;
constexpr uint32_t OFF_CH0 = 188416;
constexpr uint32_t OFF_KVS = OFF_CH0, KVS_V = 4480, KVS_BYTES = 8576;
constexpr uint32_t OFF_WS = OFF_WA;
__device__ __forceinline__ uint32_t off_us(int s) { return OFF_CH0 + 4096 * ((0x65320 >> (4 * s)) & 7); }
constexpr uint32_t OFF_YT = 163840;
constexpr uint32_t OFF_BAR = 231936;
constexpr uint32_t SMEM_BYTES = OFF_BAR + 512;

enum : uint32_t {
  B_FULL1 = 0, B_EMPTY1 = 4, B_S3 = 7, B_FULL2 = 52, B_EMPTY2 = 13, B_U = 8, B_GATE = 12, B_HA = 19, B_HB = 20,
  B_ATTN = 21, B_C34 = 22, B_YRB = 23, B_YFULL = 24, B_EPOCH = 25, B_PREP = 26, B_P1 = 27, B_LAST = 28,
  B_E3 = 29, B_OSIG = 30, B_WOP = 31, B_USIG = 32, B_WST = 33, B_KV = 34, B_KVD = 39, B_QF = 17, B_ATT2 = 18, B_YST = 40,
  B_ORB = 45, B_US = 45, B_YSIG = 50
};
constexpr uint32_t OFF_EPOCH = OFF_BAR + 8 * 51, OFF_D = OFF_BAR + 8 * 60;
__device__ __forceinline__ uint32_t off_o(int j) { return j < 4 ? OFF_OA + j * O_BYTES : j < 6 ? OFF_CH0 + (j - 4) * O_BYTES : OFF_OA + (j - 6) * O_BYTES; }
__device__ __forceinline__ uint32_t off_w(int j) { return j < 4 ? OFF_WA + j * WO_BYTES : j == 4 ? OFF_KVX : j == 5 ? OFF_WC : OFF_WA + (j - 6) * WO_BYTES; }
__device__ __forceinline__ int step_src(int hg, int j) {
  if (SRC_ROT == 2) {
    const int pos = (0x37621540 >> (4 * hg)) & 7;
    return j == 0 ? hg : (0x65217430 >> (4 * (j <= pos ? j - 1 : j))) & 7;
  }
  return SRC_ROT ? (hg + j) & 7 : j == 0 ? hg : j <= hg ? j - 1 : j;
}
__device__ __forceinline__ bool tail_first(int hg) { return TAILF && (hg & 3) == 3; }
__device__ __forceinline__ uint32_t off_ch(int c) { return (c < 3 ? OFF_CH0 : OFF_CH3 - 3 * CH_BYTES) + c * CH_BYTES; }

#define U_PITCH 264
__device__ __align__(1024) uint4 g_U[DIM * U_PITCH];
__device__ uint4 g_O[NCTA * 1280];
#define g_Y g_U
constexpr int Y_PITCH = U_PITCH;
__device__ uint4 g_WO[64 * 800];
__device__ uint4 g_halo[NCTA * 2 * 7 * 32];
__device__ float g_gate[SEQ + PAD_KB * 256];
__device__ unsigned g_cnt[32 * (1 + 2 * 16 + 8 + NCTA)];
constexpr int C_LAUNCH = 0, C_PREP = 32, C_Y = 32 * 17, C_W = 32 * 33, C_O = 32 * 41;

#define TSM(cond, slot) do { } while (0)
#define TSIF(cond, slot) do { if (__LINE__ >= FENCE_LO && __LINE__ < FENCE_HI) sched_fence(); } while (0)
__device__ __forceinline__ void sched_fence() {
  asm volatile("{\n.reg .pred p;\n.reg .u32 c;\nmov.u32 c, %%clock;\nsetp.eq.u32 p, c, 0;\n@p st.shared.u32 [%0], c;\n}"
               ::"r"(1024 + OFF_EPOCH + 4) : "memory");
}
#define TS(slot) TSIF(true, slot)

struct Params {
  const __nv_bfloat16 *q, *k, *v, *shift_k, *ssm_k, *ssm_D, *wqkv, *wo, *gate_w;
  __nv_bfloat16* out;
  uint32_t zero;
};

#define POLL_NS 0
constexpr int SPIN_LIMIT = 1 << 17;

__device__ __forceinline__ void mbar_init(uint32_t bar, uint32_t count) {
  asm volatile("mbarrier.init.shared::cta.b64 [%0], %1;" ::"r"(bar), "r"(count) : "memory");
}
__device__ __forceinline__ void mbar_expect_tx(uint32_t bar, uint32_t bytes) {
  asm volatile("mbarrier.arrive.expect_tx.shared::cta.b64 _, [%0], %1;" ::"r"(bar), "r"(bytes) : "memory");
}
__device__ __forceinline__ void mbar_arrive(uint32_t bar) {
  asm volatile("mbarrier.arrive.shared::cta.b64 _, [%0];" ::"r"(bar) : "memory");
}
__device__ __forceinline__ void mbar_wait(uint32_t bar, uint32_t parity) {
  uint32_t ok;
  int spins = 0;
  do {
    if (WAIT_NS)
      asm volatile("{\n.reg .pred p;\nmbarrier.try_wait.parity.shared::cta.b64 p, [%1], %2, %3;\nselp.b32 %0, 1, 0, p;\n}"
                   : "=r"(ok) : "r"(bar), "r"(parity), "r"(WAIT_NS) : "memory");
    else
      asm volatile("{\n.reg .pred p;\nmbarrier.try_wait.parity.shared::cta.b64 p, [%1], %2;\nselp.b32 %0, 1, 0, p;\n}"
                   : "=r"(ok) : "r"(bar), "r"(parity) : "memory");
    if (++spins > SPIN_LIMIT) break;
  } while (!ok);
}
__device__ __forceinline__ unsigned flag_read(const unsigned* p) {
  unsigned v;
  asm volatile("ld.relaxed.gpu.global.u32 %0, [%1];" : "=r"(v) : "l"(p) : "memory");
  return v;
}
__device__ __forceinline__ void flag_poll(const unsigned* p, unsigned target) {
  unsigned v;
  int spins = 0;
  do {
    if (POLL_NS && spins) __nanosleep(POLL_NS);
    asm volatile("ld.relaxed.gpu.global.u32 %0, [%1];" : "=r"(v) : "l"(p) : "memory");
    if (++spins > SPIN_LIMIT) break;
  } while ((int)(v - target) < 0);
}
__device__ __forceinline__ void flag_wait(const unsigned* p, unsigned target) {
  flag_poll(p, target);
  if (ACQ) asm volatile("fence.acquire.gpu;\nfence.proxy.async.global;" ::: "memory");
}
__device__ __forceinline__ void flag_signal(unsigned* p, int n, int lane) {
  if (lane == 0) asm volatile("fence.release.gpu;" ::: "memory");
  __syncwarp();
  if (lane < n) asm volatile("red.relaxed.gpu.global.add.u32 [%0], 1;" ::"l"(p + 32 * lane) : "memory");
}
__device__ __forceinline__ void flag_bump(unsigned* p) {
  asm volatile("red.relaxed.gpu.global.add.u32 [%0], 1;" ::"l"(p) : "memory");
}
__device__ __forceinline__ void fence_async_smem() { asm volatile("fence.proxy.async.shared::cta;" ::: "memory"); }
__device__ __forceinline__ void wg_sync(int id) { asm volatile("bar.sync %0, 128;" ::"r"(id) : "memory"); }

__device__ __forceinline__ void tma_2d(uint32_t dst, const CUtensorMap* tm, int c0, int c1, uint32_t bar) {
  asm volatile("cp.async.bulk.tensor.2d.shared::cluster.global.mbarrier::complete_tx::bytes [%0], [%1, {%3, %4}], [%2];"
               ::"r"(dst), "l"(tm), "r"(bar), "r"(c0), "r"(c1) : "memory");
}
__device__ __forceinline__ void tma_3d(uint32_t dst, const CUtensorMap* tm, int c0, int c1, int c2, uint32_t bar) {
  asm volatile("cp.async.bulk.tensor.3d.shared::cluster.global.mbarrier::complete_tx::bytes [%0], [%1, {%3, %4, %5}], [%2];"
               ::"r"(dst), "l"(tm), "r"(bar), "r"(c0), "r"(c1), "r"(c2) : "memory");
}
__device__ __forceinline__ void bulk_load(uint32_t dst, const void* src, uint32_t bytes, uint32_t bar) {
  asm volatile("cp.async.bulk.shared::cluster.global.mbarrier::complete_tx::bytes [%0], [%1], %2, [%3];"
               ::"r"(dst), "l"(src), "r"(bytes), "r"(bar) : "memory");
}
__device__ __forceinline__ void tm_prefetch(const CUtensorMap* tm) {
  asm volatile("prefetch.tensormap [%0];" ::"l"(tm) : "memory");
}

__device__ __forceinline__ void wg_fence() { asm volatile("wgmma.fence.sync.aligned;" ::: "memory"); }
__device__ __forceinline__ void wg_commit() { asm volatile("wgmma.commit_group.sync.aligned;" ::: "memory"); }
template <int N> __device__ __forceinline__ void wg_wait() { asm volatile("wgmma.wait_group.sync.aligned %0;" ::"n"(N) : "memory"); }
__device__ __forceinline__ uint32_t desc_lo(uint32_t addr, uint32_t lbo) { return ((addr & 0x3FFFF) >> 4) | ((lbo >> 4) << 16); }
constexpr uint32_t desc_hi(uint32_t sbo, uint32_t swz) { return (sbo >> 4) | (swz << 30); }
constexpr uint32_t HI_SW128 = desc_hi(1024, 1), HI_SW64 = desc_hi(512, 2), HI_SW32 = desc_hi(256, 3), HI_NONE = desc_hi(128, 0);
template <int N> __device__ __forceinline__ void pin(float* d) {
#pragma unroll
  for (int i = 0; i < N; i++) asm volatile("" : "+f"(d[i])::"memory");
}

__device__ __forceinline__ uint32_t lds32(uint32_t a) {
  uint32_t v;
  asm volatile("ld.volatile.shared.u32 %0, [%1];" : "=r"(v) : "r"(a) : "memory");
  return v;
}
__device__ __forceinline__ uint4 ldg128(const void* a) {
  uint4 v;
  asm volatile("ld.global.nc.v4.u32 {%0, %1, %2, %3}, [%4];" : "=r"(v.x), "=r"(v.y), "=r"(v.z), "=r"(v.w) : "l"(a) : "memory");
  return v;
}
__device__ __forceinline__ uint2 ldg64(const void* a) {
  uint2 v;
  asm volatile("ld.global.nc.v2.u32 {%0, %1}, [%2];" : "=r"(v.x), "=r"(v.y) : "l"(a) : "memory");
  return v;
}
__device__ __forceinline__ void ldsm4(uint32_t* r, uint32_t a) {
  asm volatile("ldmatrix.sync.aligned.m8n8.x4.shared.b16 {%0, %1, %2, %3}, [%4];"
               : "=r"(r[0]), "=r"(r[1]), "=r"(r[2]), "=r"(r[3]) : "r"(a) : "memory");
}
__device__ __forceinline__ void ldsm4t(uint32_t* r, uint32_t a) {
  asm volatile("ldmatrix.sync.aligned.m8n8.x4.trans.shared.b16 {%0, %1, %2, %3}, [%4];"
               : "=r"(r[0]), "=r"(r[1]), "=r"(r[2]), "=r"(r[3]) : "r"(a) : "memory");
}
__device__ __forceinline__ uint2 lds64(uint32_t a) {
  uint2 v;
  asm volatile("ld.shared.v2.u32 {%0, %1}, [%2];" : "=r"(v.x), "=r"(v.y) : "r"(a) : "memory");
  return v;
}
__device__ __forceinline__ uint4 lds128(uint32_t a) {
  uint4 v;
  asm volatile("ld.shared.v4.u32 {%0, %1, %2, %3}, [%4];" : "=r"(v.x), "=r"(v.y), "=r"(v.z), "=r"(v.w) : "r"(a) : "memory");
  return v;
}
__device__ __forceinline__ void sts128(uint32_t a, uint32_t x, uint32_t y, uint32_t z, uint32_t w) {
  asm volatile("st.shared.v4.u32 [%0], {%1, %2, %3, %4};" ::"r"(a), "r"(x), "r"(y), "r"(z), "r"(w) : "memory");
}
__device__ __forceinline__ void stsm4(uint32_t a, const uint32_t* r) {
  asm volatile("stmatrix.sync.aligned.m8n8.x4.shared.b16 [%0], {%1, %2, %3, %4};" ::"r"(a), "r"(r[0]), "r"(r[1]), "r"(r[2]), "r"(r[3]) : "memory");
}
__device__ __forceinline__ void stsm4t(uint32_t a, const uint32_t* r) {
  asm volatile("stmatrix.sync.aligned.m8n8.x4.trans.shared.b16 [%0], {%1, %2, %3, %4};" ::"r"(a), "r"(r[0]), "r"(r[1]), "r"(r[2]), "r"(r[3]) : "memory");
}
__device__ __forceinline__ uint32_t pack2(float lo, float hi) {
  uint32_t r;
  asm("cvt.rn.bf16x2.f32 %0, %1, %2;" : "=r"(r) : "f"(hi), "f"(lo));
  return r;
}
__device__ __forceinline__ uint32_t movm(uint32_t a) {
  uint32_t d;
  asm volatile("movmatrix.sync.aligned.m8n8.trans.b16 %0, %1;" : "=r"(d) : "r"(a));
  return d;
}
__device__ __forceinline__ uint32_t bmul(uint32_t a, uint32_t b) {
  uint32_t d;
  asm("mul.rn.bf16x2 %0, %1, %2;" : "=r"(d) : "r"(a), "r"(b));
  return d;
}
__device__ __forceinline__ uint32_t badd(uint32_t a, uint32_t b) {
  uint32_t d;
  asm("add.rn.bf16x2 %0, %1, %2;" : "=r"(d) : "r"(a), "r"(b));
  return d;
}
__device__ __forceinline__ uint32_t bfma(uint32_t a, uint32_t b, uint32_t c) {
  uint32_t d;
  asm("fma.rn.bf16x2 %0, %1, %2, %3;" : "=r"(d) : "r"(a), "r"(b), "r"(c));
  return d;
}
__device__ __forceinline__ float bf_lo(uint32_t x) { return __uint_as_float(x << 16); }
__device__ __forceinline__ float bf_hi(uint32_t x) { return __uint_as_float(x & 0xFFFF0000u); }
__device__ __forceinline__ float ex2(float x) {
  float y;
  asm("ex2.approx.ftz.f32 %0, %1;" : "=f"(y) : "f"(x));
  return y;
}
__device__ __forceinline__ float rcp(float x) {
  float y;
  asm("rcp.approx.ftz.f32 %0, %1;" : "=f"(y) : "f"(x));
  return y;
}
__device__ __forceinline__ void mma16816(float* d, uint32_t a0, uint32_t a1, uint32_t a2, uint32_t a3, uint32_t b0, uint32_t b1) {
  asm volatile("mma.sync.aligned.m16n8k16.row.col.f32.bf16.bf16.f32 {%0, %1, %2, %3}, {%4, %5, %6, %7}, {%8, %9}, {%0, %1, %2, %3};"
               : "+f"(d[0]), "+f"(d[1]), "+f"(d[2]), "+f"(d[3])
               : "r"(a0), "r"(a1), "r"(a2), "r"(a3), "r"(b0), "r"(b1));
}
__device__ __forceinline__ void mma1688(float* d, uint32_t a0, uint32_t a1, uint32_t b0) {
  asm volatile("mma.sync.aligned.m16n8k8.row.col.f32.bf16.bf16.f32 {%0, %1, %2, %3}, {%4, %5}, {%6}, {%0, %1, %2, %3};"
               : "+f"(d[0]), "+f"(d[1]), "+f"(d[2]), "+f"(d[3])
               : "r"(a0), "r"(a1), "r"(b0));
}

template <int N> struct WgRS;
template <int N> struct WgSST;
template <> struct WgRS<32> {
  template <uint32_t HB>
  static __device__ __forceinline__ void mma(float* d, const uint32_t* a, uint32_t db) {
    asm volatile("{\n.reg .pred p;\n.reg .b64 db;\nsetp.ne.b32 p, %22, 0;\n"
      "mov.b64 db, {%20, %21};\n"
      "wgmma.mma_async.sync.aligned.m64n32k16.f32.bf16.bf16 {"
      "%0, %1, %2, %3, %4, %5, %6, %7, %8, %9, %10, %11, %12, %13, %14, %15"
      "}, {%16, %17, %18, %19}, db, p, 1, 1, 1;\n}\n"
      : "+f"(d[0]), "+f"(d[1]), "+f"(d[2]), "+f"(d[3]), "+f"(d[4]), "+f"(d[5]), "+f"(d[6]), "+f"(d[7]),
        "+f"(d[8]), "+f"(d[9]), "+f"(d[10]), "+f"(d[11]), "+f"(d[12]), "+f"(d[13]), "+f"(d[14]), "+f"(d[15])
      : "r"(a[0]), "r"(a[1]), "r"(a[2]), "r"(a[3]), "r"(db), "n"(HB), "n"(1));
  }
  template <uint32_t HB>
  static __device__ __forceinline__ void set(float* d, const uint32_t* a, uint32_t db) {
    asm volatile("{\n.reg .pred p;\n.reg .b64 db;\nsetp.ne.b32 p, %22, 0;\n"
      "mov.b64 db, {%20, %21};\n"
      "wgmma.mma_async.sync.aligned.m64n32k16.f32.bf16.bf16 {"
      "%0, %1, %2, %3, %4, %5, %6, %7, %8, %9, %10, %11, %12, %13, %14, %15"
      "}, {%16, %17, %18, %19}, db, p, 1, 1, 1;\n}\n"
      : "=f"(d[0]), "=f"(d[1]), "=f"(d[2]), "=f"(d[3]), "=f"(d[4]), "=f"(d[5]), "=f"(d[6]), "=f"(d[7]),
        "=f"(d[8]), "=f"(d[9]), "=f"(d[10]), "=f"(d[11]), "=f"(d[12]), "=f"(d[13]), "=f"(d[14]), "=f"(d[15])
      : "r"(a[0]), "r"(a[1]), "r"(a[2]), "r"(a[3]), "r"(db), "n"(HB), "n"(0));
  }
};
template <> struct WgRS<64> {
  template <uint32_t HB>
  static __device__ __forceinline__ void mma(float* d, const uint32_t* a, uint32_t db) {
    asm volatile("{\n.reg .pred p;\n.reg .b64 db;\nsetp.ne.b32 p, %38, 0;\n"
      "mov.b64 db, {%36, %37};\n"
      "wgmma.mma_async.sync.aligned.m64n64k16.f32.bf16.bf16 {"
      "%0, %1, %2, %3, %4, %5, %6, %7, %8, %9, %10, %11, %12, %13, %14, %15, "
      "%16, %17, %18, %19, %20, %21, %22, %23, %24, %25, %26, %27, %28, %29, %30, %31"
      "}, {%32, %33, %34, %35}, db, p, 1, 1, 1;\n}\n"
      : "+f"(d[0]), "+f"(d[1]), "+f"(d[2]), "+f"(d[3]), "+f"(d[4]), "+f"(d[5]), "+f"(d[6]), "+f"(d[7]),
        "+f"(d[8]), "+f"(d[9]), "+f"(d[10]), "+f"(d[11]), "+f"(d[12]), "+f"(d[13]), "+f"(d[14]), "+f"(d[15]),
        "+f"(d[16]), "+f"(d[17]), "+f"(d[18]), "+f"(d[19]), "+f"(d[20]), "+f"(d[21]), "+f"(d[22]), "+f"(d[23]),
        "+f"(d[24]), "+f"(d[25]), "+f"(d[26]), "+f"(d[27]), "+f"(d[28]), "+f"(d[29]), "+f"(d[30]), "+f"(d[31])
      : "r"(a[0]), "r"(a[1]), "r"(a[2]), "r"(a[3]), "r"(db), "n"(HB), "n"(1));
  }
  template <uint32_t HB>
  static __device__ __forceinline__ void set(float* d, const uint32_t* a, uint32_t db) {
    asm volatile("{\n.reg .pred p;\n.reg .b64 db;\nsetp.ne.b32 p, %38, 0;\n"
      "mov.b64 db, {%36, %37};\n"
      "wgmma.mma_async.sync.aligned.m64n64k16.f32.bf16.bf16 {"
      "%0, %1, %2, %3, %4, %5, %6, %7, %8, %9, %10, %11, %12, %13, %14, %15, "
      "%16, %17, %18, %19, %20, %21, %22, %23, %24, %25, %26, %27, %28, %29, %30, %31"
      "}, {%32, %33, %34, %35}, db, p, 1, 1, 1;\n}\n"
      : "=f"(d[0]), "=f"(d[1]), "=f"(d[2]), "=f"(d[3]), "=f"(d[4]), "=f"(d[5]), "=f"(d[6]), "=f"(d[7]),
        "=f"(d[8]), "=f"(d[9]), "=f"(d[10]), "=f"(d[11]), "=f"(d[12]), "=f"(d[13]), "=f"(d[14]), "=f"(d[15]),
        "=f"(d[16]), "=f"(d[17]), "=f"(d[18]), "=f"(d[19]), "=f"(d[20]), "=f"(d[21]), "=f"(d[22]), "=f"(d[23]),
        "=f"(d[24]), "=f"(d[25]), "=f"(d[26]), "=f"(d[27]), "=f"(d[28]), "=f"(d[29]), "=f"(d[30]), "=f"(d[31])
      : "r"(a[0]), "r"(a[1]), "r"(a[2]), "r"(a[3]), "r"(db), "n"(HB), "n"(0));
  }
};
template <> struct WgSST<48> {
  template <uint32_t HA, uint32_t HB>
  static __device__ __forceinline__ void mma(float* d, uint32_t da, uint32_t db, int sc) {
    asm volatile("{\n.reg .pred p;\n.reg .b64 da, db;\nsetp.ne.b32 p, %28, 0;\n"
      "mov.b64 da, {%24, %25};\nmov.b64 db, {%26, %27};\n"
      "wgmma.mma_async.sync.aligned.m64n48k16.f32.bf16.bf16 {"
      "%0, %1, %2, %3, %4, %5, %6, %7, %8, %9, %10, %11, %12, %13, %14, %15, "
      "%16, %17, %18, %19, %20, %21, %22, %23"
      "}, da, db, p, 1, 1, 0, 1;\n}\n"
      : "+f"(d[0]), "+f"(d[1]), "+f"(d[2]), "+f"(d[3]), "+f"(d[4]), "+f"(d[5]), "+f"(d[6]), "+f"(d[7]),
        "+f"(d[8]), "+f"(d[9]), "+f"(d[10]), "+f"(d[11]), "+f"(d[12]), "+f"(d[13]), "+f"(d[14]), "+f"(d[15]),
        "+f"(d[16]), "+f"(d[17]), "+f"(d[18]), "+f"(d[19]), "+f"(d[20]), "+f"(d[21]), "+f"(d[22]), "+f"(d[23])
      : "r"(da), "n"(HA), "r"(db), "n"(HB), "r"(sc));
  }
};
template <> struct WgSST<80> {
  template <uint32_t HA, uint32_t HB>
  static __device__ __forceinline__ void mma(float* d, uint32_t da, uint32_t db, int sc) {
    asm volatile("{\n.reg .pred p;\n.reg .b64 da, db;\nsetp.ne.b32 p, %44, 0;\n"
      "mov.b64 da, {%40, %41};\nmov.b64 db, {%42, %43};\n"
      "wgmma.mma_async.sync.aligned.m64n80k16.f32.bf16.bf16 {"
      "%0, %1, %2, %3, %4, %5, %6, %7, %8, %9, %10, %11, %12, %13, %14, %15, "
      "%16, %17, %18, %19, %20, %21, %22, %23, %24, %25, %26, %27, %28, %29, %30, %31, "
      "%32, %33, %34, %35, %36, %37, %38, %39"
      "}, da, db, p, 1, 1, 0, 1;\n}\n"
      : "+f"(d[0]), "+f"(d[1]), "+f"(d[2]), "+f"(d[3]), "+f"(d[4]), "+f"(d[5]), "+f"(d[6]), "+f"(d[7]),
        "+f"(d[8]), "+f"(d[9]), "+f"(d[10]), "+f"(d[11]), "+f"(d[12]), "+f"(d[13]), "+f"(d[14]), "+f"(d[15]),
        "+f"(d[16]), "+f"(d[17]), "+f"(d[18]), "+f"(d[19]), "+f"(d[20]), "+f"(d[21]), "+f"(d[22]), "+f"(d[23]),
        "+f"(d[24]), "+f"(d[25]), "+f"(d[26]), "+f"(d[27]), "+f"(d[28]), "+f"(d[29]), "+f"(d[30]), "+f"(d[31]),
        "+f"(d[32]), "+f"(d[33]), "+f"(d[34]), "+f"(d[35]), "+f"(d[36]), "+f"(d[37]), "+f"(d[38]), "+f"(d[39])
      : "r"(da), "n"(HA), "r"(db), "n"(HB), "r"(sc));
  }
};
template <> struct WgSST<192> {
  template <uint32_t HA, uint32_t HB>
  static __device__ __forceinline__ void mma(float* d, uint32_t da, uint32_t db, int sc) {
    asm volatile("{\n.reg .pred p;\n.reg .b64 da, db;\nsetp.ne.b32 p, %100, 0;\n"
      "mov.b64 da, {%96, %97};\nmov.b64 db, {%98, %99};\n"
      "wgmma.mma_async.sync.aligned.m64n192k16.f32.bf16.bf16 {"
      "%0, %1, %2, %3, %4, %5, %6, %7, %8, %9, %10, %11, %12, %13, %14, %15, "
      "%16, %17, %18, %19, %20, %21, %22, %23, %24, %25, %26, %27, %28, %29, %30, %31, "
      "%32, %33, %34, %35, %36, %37, %38, %39, %40, %41, %42, %43, %44, %45, %46, %47, "
      "%48, %49, %50, %51, %52, %53, %54, %55, %56, %57, %58, %59, %60, %61, %62, %63, "
      "%64, %65, %66, %67, %68, %69, %70, %71, %72, %73, %74, %75, %76, %77, %78, %79, "
      "%80, %81, %82, %83, %84, %85, %86, %87, %88, %89, %90, %91, %92, %93, %94, %95"
      "}, da, db, p, 1, 1, 0, 1;\n}\n"
      : "+f"(d[0]), "+f"(d[1]), "+f"(d[2]), "+f"(d[3]), "+f"(d[4]), "+f"(d[5]), "+f"(d[6]), "+f"(d[7]),
        "+f"(d[8]), "+f"(d[9]), "+f"(d[10]), "+f"(d[11]), "+f"(d[12]), "+f"(d[13]), "+f"(d[14]), "+f"(d[15]),
        "+f"(d[16]), "+f"(d[17]), "+f"(d[18]), "+f"(d[19]), "+f"(d[20]), "+f"(d[21]), "+f"(d[22]), "+f"(d[23]),
        "+f"(d[24]), "+f"(d[25]), "+f"(d[26]), "+f"(d[27]), "+f"(d[28]), "+f"(d[29]), "+f"(d[30]), "+f"(d[31]),
        "+f"(d[32]), "+f"(d[33]), "+f"(d[34]), "+f"(d[35]), "+f"(d[36]), "+f"(d[37]), "+f"(d[38]), "+f"(d[39]),
        "+f"(d[40]), "+f"(d[41]), "+f"(d[42]), "+f"(d[43]), "+f"(d[44]), "+f"(d[45]), "+f"(d[46]), "+f"(d[47]),
        "+f"(d[48]), "+f"(d[49]), "+f"(d[50]), "+f"(d[51]), "+f"(d[52]), "+f"(d[53]), "+f"(d[54]), "+f"(d[55]),
        "+f"(d[56]), "+f"(d[57]), "+f"(d[58]), "+f"(d[59]), "+f"(d[60]), "+f"(d[61]), "+f"(d[62]), "+f"(d[63]),
        "+f"(d[64]), "+f"(d[65]), "+f"(d[66]), "+f"(d[67]), "+f"(d[68]), "+f"(d[69]), "+f"(d[70]), "+f"(d[71]),
        "+f"(d[72]), "+f"(d[73]), "+f"(d[74]), "+f"(d[75]), "+f"(d[76]), "+f"(d[77]), "+f"(d[78]), "+f"(d[79]),
        "+f"(d[80]), "+f"(d[81]), "+f"(d[82]), "+f"(d[83]), "+f"(d[84]), "+f"(d[85]), "+f"(d[86]), "+f"(d[87]),
        "+f"(d[88]), "+f"(d[89]), "+f"(d[90]), "+f"(d[91]), "+f"(d[92]), "+f"(d[93]), "+f"(d[94]), "+f"(d[95])
      : "r"(da), "n"(HA), "r"(db), "n"(HB), "r"(sc));
  }
};

struct FftConst {
  uint32_t f[2][4], fi[4][4];
  uint32_t ta[2][2], tb[2][2];
};
__device__ __forceinline__ void cis(int m, float scale, float& c, float& s) {
  const float a = (float)m * (-6.283185307179586f * scale);
  c = __cosf(a);
  s = __sinf(a);
}
__device__ __forceinline__ void fft_tables(uint32_t (&v)[12], int tw) {
  const int row = tw >> 2, ch = tw & 3;
#pragma unroll
  for (int i = 0; i < 4; i++) {
    float c[2], s[2], x[2];
#pragma unroll
    for (int e = 0; e < 2; e++) {
      cis((((32 * (8 * ch + 2 * i + e) + 15) * (4 * row - 63) + 2048) & 4095) - 2048, 1.f / 4096, c[e], s[e]);
      float gc, gs;
      cis((((row & 15) * (8 * (ch & 1) + 2 * i + e) + 8) & 15) - 8, 1.f / 16, gc, gs);
      x[e] = (row >> 4) == (ch >> 1) ? gc : (ch >> 1) ? gs : -gs;
    }
    v[i] = pack2(c[0] * 0.125f, c[1] * 0.125f);
    v[4 + i] = pack2(s[0] * 0.125f, s[1] * 0.125f);
    v[8 + i] = pack2(x[0], x[1]);
  }
#pragma unroll
  for (int i = 0; i < 12; i++) asm volatile("" : "+r"(v[i]));
}
__device__ __forceinline__ void fft_tables_store(const uint32_t (&v)[12], uint32_t sb, int tw) {
  const int row = tw >> 2;
  const uint32_t x = ((tw ^ (row >> 1)) & 3) << 4, a = sb + OFF_FT + (16 * (row >> 3) + (row & 7)) * 64 + x;
  sts128(a, v[0], v[1], v[2], v[3]);
  sts128(a + 512, v[4], v[5], v[6], v[7]);
  sts128(sb + OFF_GT + row * 64 + x, v[8], v[9], v[10], v[11]);
}
__device__ __forceinline__ void fft_twiddles(uint32_t (&v)[2], int tw) {
  float a[2], s[2];
#pragma unroll
  for (int i = 0; i < 2; i++) {
    float c;
    cis((2 * (2 * (tw & 3) + i) - 15) * (4 * (tw >> 2) - 63), 1.f / 4096, c, s[i]);
    a[i] = __fdividef(-s[i], 1.f + c);
  }
  v[0] = pack2(a[0], a[1]);
  v[1] = pack2(s[0], s[1]);
  asm volatile("" : "+r"(v[0]), "+r"(v[1]));
}
__device__ __forceinline__ void fft_matrices(FftConst& k, uint32_t sb, int w, int lane) {
  const uint32_t x = (lane >> 1) & 3;
  const uint2 t0 = lds64(sb + OFF_TT + 256 * w + 8 * lane), t1 = lds64(sb + OFF_TT + 256 * w + 8 * (lane ^ 3));
  k.ta[0][0] = t0.x;
  k.tb[0][0] = t0.y;
  k.ta[1][1] = __byte_perm(t1.x, 0, 0x1032);
  k.tb[1][1] = __byte_perm(t1.y, 0, 0x1032);
#pragma unroll
  for (int j = 0; j < 2; j++) {
    k.ta[1 - j][j] = k.ta[j][j] ^ 0x80008000u;
    k.tb[1 - j][j] = k.tb[j][j] ^ 0x80008000u;
    asm volatile("" : "+r"(k.ta[0][j]), "+r"(k.tb[0][j]), "+r"(k.ta[1][j]), "+r"(k.tb[1][j]));
  }
#pragma unroll
  for (int i = 0; i < 2; i++) {
    ldsm4(k.f[i], sb + OFF_FT + (16 * w + (lane & 15)) * 64 + (((2 * i + (lane >> 4)) ^ x) << 4));
    ldsm4t(k.fi[i], sb + OFF_FT + (32 * i + lane) * 64 + ((w ^ x) << 4));
#pragma unroll
    for (int j = 0; j < 4; j++) {
      k.fi[2 + i][j] = (j & 1) ? k.fi[i][j - 1] ^ 0x80008000u : k.fi[i][j + 1];
      asm volatile("" : "+r"(k.fi[2 + i][j]));
    }
  }
}
__device__ __forceinline__ void rot(uint32_t& x, uint32_t& y, uint32_t a, uint32_t b) {
  x = bfma(a, y, x);
  y = bfma(b, x, y);
  x = bfma(a, y, x);
}
__device__ __forceinline__ void twiddle_fwd(uint32_t (&a)[4][4], float* d, const FftConst& k) {
#pragma unroll
  for (int q = 0; q < 4; q++)
#pragma unroll
    for (int j = 0; j < 2; j++) {
      const float* x = d + 8 * q + 4 * j;
      uint32_t re = pack2(x[0], x[1]), im = pack2(x[2], x[3]);
      rot(re, im, k.ta[0][j], k.tb[0][j]);
      a[q & 2][2 * j + (q & 1)] = re;
      a[(q & 2) + 1][2 * j + (q & 1)] = im;
    }
}
__device__ __forceinline__ void g_step(float* d, const uint32_t (&a)[4][4], uint32_t dre, uint32_t dim) {
  WgRS<32>::set<HI_SW64>(d, a[0], dre);
  WgRS<32>::set<HI_SW64>(d + 16, a[2], dre);
  WgRS<32>::mma<HI_SW64>(d, a[1], dim);
  WgRS<32>::mma<HI_SW64>(d + 16, a[3], dim);
  wg_commit();
}

__device__ __forceinline__ void conv_channel(const FftConst& k, uint32_t sb, int c, int wg, int w, int lane) {
  const uint32_t cb = sb + off_ch(c), bars = sb + OFF_BAR;
  const uint32_t du = desc_lo(cb, 1024), dg = desc_lo(sb + OFF_GT, 16), dz = desc_lo(cb + U_BYTES, 16);
  float U[32], H[32];
  uint32_t a[4][4], e[4][4];
  const float dv = __uint_as_float(lds32(sb + OFF_D + 4 * c));
  wg_fence();
  WgRS<64>::set<HI_SW32>(H, k.f[0], du + 256);
  WgRS<64>::mma<HI_SW32>(H, k.f[1], du + 256 + 32);
  wg_commit();
  wg_wait<0>();
  pin<32>(H);
  twiddle_fwd(a, H, k);
  if (ATT_GATE) mbar_wait(bars + 8 * (ATT_GATE == 1 ? B_ATTN : B_ATT2), 0);
  mbar_wait(bars + 8 * (B_U + (c < 3 ? c : 3)), 0);
  TSM(w == 0 && c < 3, 7 + wg);
  wg_fence();
  WgRS<64>::set<HI_SW32>(U, k.f[0], du);
  WgRS<64>::mma<HI_SW32>(U, k.f[1], du + 32);
  wg_commit();
  g_step(H, a, dg, dg + 64);
  wg_wait<1>();
  pin<32>(U);
  twiddle_fwd(e, U, k);
  wg_fence();
  g_step(U, e, dg, dg + 64);
  wg_wait<0>();
  pin<32>(U);
  pin<32>(H);
#pragma unroll
  for (int j = 0; j < 2; j++) {
    float pr[4][2], pi[4][2];
#pragma unroll
    for (int x = 0; x < 2; x++) {
      H[4 * j + x] += dv;
#pragma unroll
      for (int m = 0; m < 4; m++) {
#pragma unroll
        for (int q = 0; q <= m; q++) {
          const int ih = 16 * (q >> 1) + 2 * (q & 1) + 4 * j + x, iu = 16 * ((m - q) >> 1) + 2 * ((m - q) & 1) + 4 * j + x;
          pr[m][x] = q ? fmaf(H[ih], U[iu], pr[m][x]) : H[ih] * U[iu];
          pi[m][x] = q ? fmaf(H[ih], U[iu + 8], pi[m][x]) : H[ih] * U[iu + 8];
          pr[m][x] = fmaf(-H[ih + 8], U[iu + 8], pr[m][x]);
          pi[m][x] = fmaf(H[ih + 8], U[iu], pi[m][x]);
        }
      }
    }
#pragma unroll
    for (int m = 0; m < 4; m++) {
      a[m & 2][2 * j + (m & 1)] = pack2(pr[m][0], pr[m][1]);
      a[(m & 2) + 1][2 * j + (m & 1)] = pack2(pi[m][0], pi[m][1]);
    }
  }
  wg_fence();
  g_step(U, a, dg + 64, dg);
  const uint32_t za = cb + U_BYTES + (8 * w + (lane & 7)) * 128 + (((lane >> 3) ^ (lane & 7)) << 4);
  const uint32_t ya = cb + (lane >> 4) * 1024 + (8 * w + (lane & 7)) * 32 + ((((lane >> 3) ^ (lane >> 2)) & 1) << 4);
  wg_sync(1 + wg);
  wg_wait<0>();
  pin<32>(U);
  TSIF(w == 0, 80 + c);
#pragma unroll
  for (int p = 0; p < 2; p++) {
#pragma unroll
    for (int i = 0; i < 4; i++) {
      const int j = i & 1;
      const float* x = U + 16 * p + 4 * j + (i & 2);
      e[p][i] = pack2(x[8], x[9]);
      e[2 + p][i] = pack2(x[0], x[1]);
      rot(e[p][i], e[2 + p][i], k.ta[1][j], k.tb[1][j]);
    }
    stsm4(za ^ (64 * p), e[p]);
    stsm4((za ^ (64 * p)) + 4096, e[2 + p]);
  }
  fence_async_smem();
  wg_sync(1 + wg);
  wg_fence();
  WgRS<64>::set<HI_SW128>(H, k.fi[0], dz);
#pragma unroll
  for (int ks = 1; ks < 4; ks++) WgRS<64>::mma<HI_SW128>(H, k.fi[ks], dz + 128 * ks);
  wg_commit();
  if (WO_FAST) mbar_wait(bars + 8 * B_ATTN, 0);
  wg_wait<0>();
  pin<32>(H);
  TSIF(w == 0, 88 + c);
#pragma unroll
  for (int j = 0; j < 8; j++)
    a[j >> 2][j & 3] = j < 2 ? pack2(H[4 * j], H[4 * j + 1]) : pack2(H[4 * j] + H[4 * j - 6], H[4 * j + 1] + H[4 * j - 5]);
  stsm4(ya, a[0]);
  stsm4(ya + 2048, a[1]);
  fence_async_smem();
  __syncwarp();
}

__device__ __forceinline__ void prep_slab(uint4* res, const uint2* sw, uint32_t sb, int slab, int w, int lane) {
  const int t = lane & 3, tp = (lane & 7) >> 1, pos = 8 * tp + 2 * (((lane >> 3) + tp) & 3) + (lane & 1);
  const uint32_t base = sb + OFF_KVS + slab * KVS_BYTES + pos * 128;
  uint32_t kk[2][4][4], vv[2][4];
  mbar_wait(sb + OFF_BAR + 8 * (B_KV + slab), 0);
#pragma unroll
  for (int h = 0; h < 2; h++) {
#pragma unroll
    for (int j = 0; j < 4; j++) {
      const uint32_t a = base + 128 * j;
      ldsm4t(kk[h][j], a + (((w + 4 * h) ^ ((a >> 7) & 7)) << 4));
    }
    const uint32_t a = base + KVS_V;
    ldsm4t(vv[h], a + (((w + 4 * h) ^ ((a >> 7) & 7)) << 4));
  }
#pragma unroll
  for (int h = 0; h < 2; h++) {
    uint32_t (&k)[4][4] = kk[h];
    uint32_t (&v)[4] = vv[h];
    const uint32_t w0 = __byte_perm(sw[h].x, 0, 0x1010), w1 = __byte_perm(sw[h].x, 0, 0x3232);
    const uint32_t w2 = __byte_perm(sw[h].y, 0, 0x1010), w3 = __byte_perm(sw[h].y, 0, 0x3232);
#pragma unroll
    for (int m = 0; m < 4; m++)
      v[m] = bmul(badd(badd(badd(bmul(k[0][m], w3), bmul(k[1][m], w2)), bmul(k[2][m], w1)), bmul(k[3][m], w0)), v[m]);
    uint32_t a[4];
#pragma unroll
    for (int m = 0; m < 4; m++) a[m] = (t & 1) ? v[(m + 3) & 3] : v[m];
    res[h] = (t & 2) ? make_uint4(a[2], a[3], a[0], a[1]) : make_uint4(a[0], a[1], a[2], a[3]);
  }
}

__device__ __forceinline__ void prep_gate(const Params& p, int b, int w, int lane) {
  uint2 gw[5], x[4][5];
#pragma unroll
  for (int j = 0; j < 5; j++) gw[j] = ldg64(reinterpret_cast<const uint2*>(p.gate_w) + lane + 32 * j);
#pragma unroll
  for (int i = 0; i < 4; i++)
#pragma unroll
    for (int j = 0; j < 5; j++)
      x[i][j] = ldg64(reinterpret_cast<const uint2*>(p.q) + (16 * b + 4 * w + i) * (DIM / 4) + lane + 32 * j);
  float s[4];
#pragma unroll
  for (int i = 0; i < 4; i++) {
    s[i] = 0.f;
#pragma unroll
    for (int j = 0; j < 5; j++) {
      const uint32_t m0 = bmul(x[i][j].x, gw[j].x), m1 = bmul(x[i][j].y, gw[j].y);
      s[i] += (bf_lo(m0) + bf_hi(m0)) + (bf_lo(m1) + bf_hi(m1));
    }
  }
  const bool h = lane & 16, q = lane & 8;
  const float a = (h ? s[2] : s[0]) + __shfl_xor_sync(0xffffffffu, h ? s[0] : s[2], 16);
  const float c = (h ? s[3] : s[1]) + __shfl_xor_sync(0xffffffffu, h ? s[1] : s[3], 16);
  float z = (q ? c : a) + __shfl_xor_sync(0xffffffffu, q ? a : c, 8);
#pragma unroll
  for (int o = 4; o > 0; o >>= 1) z += __shfl_xor_sync(0xffffffffu, z, o);
  z = bf_lo(pack2(z, 0.f));
  if ((lane & 7) == 0) g_gate[16 * b + 4 * w + (lane >> 3)] = bf_lo(pack2(__fdividef(1.f, 1.f + __expf(-z)), 0.f));
}

__device__ __forceinline__ uint32_t bmax(uint32_t a, uint32_t b) {
  uint32_t d;
  asm("max.bf16x2 %0, %1, %2;" : "=r"(d) : "r"(a), "r"(b));
  return d;
}
__device__ __forceinline__ void softmax_two(const float (&l)[2][2], uint32_t& p0, uint32_t& p1) {
  constexpr float kScale = 0.22360679774997896f, kLog2e = 1.4426950408889634f;
  const uint32_t r0 = pack2(l[0][0], l[1][0]), r1 = pack2(l[0][1], l[1][1]);
  const uint32_t x0 = pack2(bf_lo(r0) * kScale, bf_hi(r0) * kScale), x1 = pack2(bf_lo(r1) * kScale, bf_hi(r1) * kScale);
  uint32_t m = bmax(x0, x1);
  m = bmax(m, __shfl_xor_sync(0xffffffffu, m, 1));
  m = bmax(m, __shfl_xor_sync(0xffffffffu, m, 2));
  const float m0 = bf_lo(m) * kLog2e, m1 = bf_hi(m) * kLog2e;
  p0 = pack2(ex2(bf_lo(x0) * kLog2e - m0), ex2(bf_lo(x1) * kLog2e - m0));
  p1 = pack2(ex2(bf_hi(x0) * kLog2e - m1), ex2(bf_hi(x1) * kLog2e - m1));
}

__device__ __forceinline__ void halo_read(uint32_t (&kpv)[10], uint32_t (&vpv)[10], uint32_t (&tg)[7], const uint4* hp) {
#pragma unroll
  for (int j = 0; j < 7; j++) {
    uint32_t x0, x1, x2;
    asm volatile("ld.relaxed.gpu.global.v4.u32 {%0, %1, %2, %3}, [%4];"
                 : "=r"(x0), "=r"(x1), "=r"(x2), "=r"(tg[j]) : "l"(hp + 32 * j) : "memory");
    if (j < 4) kpv[3 * j] = x0; else vpv[3 * j - 10] = x0;
    if (j < 3) kpv[3 * j + 1] = x1; else vpv[3 * j - 9] = x1;
    if (j < 3) kpv[3 * j + 2] = x2; else if (j < 6) vpv[3 * j - 8] = x2;
  }
}

template <int ROT>
__device__ __forceinline__ void pack_qkv(const float* acc, uint32_t (&qlo)[10], uint32_t (&qhi)[10], uint32_t (&klo)[10],
                                         uint32_t (&khi)[10], uint32_t (&vlo)[10], uint32_t (&vhi)[10]) {
#pragma unroll
  for (int j = 0; j < 10; j++) {
    const int x = (j + ROT) % 10, tq = x < 8 ? x : 16 + x, tk = x < 8 ? 8 + x : 18 + x, tv = x < 8 ? 16 + x : 20 + x;
    khi[j] = pack2(acc[4 * tk + 2], acc[4 * tk + 3]);
    vhi[j] = movm(pack2(acc[4 * tv + 2], acc[4 * tv + 3]));
    qlo[j] = pack2(acc[4 * tq], acc[4 * tq + 1]);
    qhi[j] = pack2(acc[4 * tq + 2], acc[4 * tq + 3]);
    klo[j] = pack2(acc[4 * tk], acc[4 * tk + 1]);
    vlo[j] = pack2(acc[4 * tv], acc[4 * tv + 1]);
    asm volatile("" : "+r"(khi[j]), "+r"(qlo[j]), "+r"(qhi[j]), "+r"(klo[j]), "+r"(vlo[j]));
  }
}

template <int ROT> __device__ __forceinline__ void halo_send(const float* acc, uint4* ho, uint32_t tag) {
#pragma unroll
  for (int j = 0; j < 7; j++) {
    uint32_t x[3];
#pragma unroll
    for (int e = 0; e < 3; e++) {
      const int i = 3 * j + e, y = (i % 10 + ROT) % 10, tk = y < 8 ? 8 + y : 18 + y, tv = y < 8 ? 16 + y : 20 + y;
      x[e] = i < 10 ? pack2(acc[4 * tk + 2], acc[4 * tk + 3]) : i < 20 ? movm(pack2(acc[4 * tv + 2], acc[4 * tv + 3])) : 0u;
    }
    asm volatile("st.relaxed.gpu.global.v4.u32 [%0], {%1, %2, %3, %4};" ::"l"(ho + 32 * j), "r"(x[0]), "r"(x[1]), "r"(x[2]), "r"(tag) : "memory");
  }
}

__device__ __forceinline__ void attention(float* acc, uint32_t sb, int b, int par, int w, int lane, uint32_t tag, uint32_t zero) {
  const int g = lane >> 2, t = lane & 3;
  uint32_t klo[10], khi[10], vlo[10], vhi[10], qlo[10], qhi[10], kpv[10], vpv[10];
  if (HALO_FIRST && w == 3 && b < NCTA - 8) {
    uint4* ho = g_halo + (b * 2 + par) * 224 + lane;
    if (tail_first(b & 7)) halo_send<8>(acc, ho, tag);
    else halo_send<0>(acc, ho, tag);
    TSIF(par == 0, 76);
    pin<120>(acc);
  }
  if (tail_first(b & 7)) pack_qkv<8>(acc, qlo, qhi, klo, khi, vlo, vhi);
  else pack_qkv<0>(acc, qlo, qhi, klo, khi, vlo, vhi);
  const uint32_t xa = sb + OFF_KVX + (par * 3) * 2560 + lane * 16;
  if (w < 3) {
    sts128(xa + w * 2560, khi[0], khi[1], khi[2], khi[3]);
    sts128(xa + w * 2560 + 512, khi[4], khi[5], khi[6], khi[7]);
    sts128(xa + w * 2560 + 1024, khi[8], khi[9], vhi[0], vhi[1]);
    sts128(xa + w * 2560 + 1536, vhi[2], vhi[3], vhi[4], vhi[5]);
    sts128(xa + w * 2560 + 2048, vhi[6], vhi[7], vhi[8], vhi[9]);
  } else if (!HALO_FIRST && b < NCTA - 8) {
    uint4* ho = g_halo + (b * 2 + par) * 224 + lane;
#pragma unroll
    for (int j = 0; j < 7; j++) {
      const uint32_t x0 = j < 4 ? khi[3 * j] : vhi[3 * j - 10], x1 = j < 3 ? khi[3 * j + 1] : vhi[3 * j - 9];
      const uint32_t x2 = j < 3 ? khi[3 * j + 2] : j < 6 ? vhi[3 * j - 8] : 0u;
      asm volatile("st.relaxed.gpu.global.v4.u32 [%0], {%1, %2, %3, %4};" ::"l"(ho + 32 * j), "r"(x0), "r"(x1), "r"(x2), "r"(tag) : "memory");
    }
  }
  TSIF(par == 0 && w == 1, 64);
  TSIF(par == 0 && w == 3 && !HALO_FIRST, 76);
#pragma unroll
  for (int j = 0; j < 10; j++) vlo[j] = movm(vlo[j]);
  const bool far0 = 2 * t > g, far1 = 2 * t + 1 > g;
  const uint32_t mfar = (far0 ? 0x0000FFFFu : 0u) | (far1 ? 0xFFFF0000u : 0u);
  float slo[4][2], shi[4][2], lg[2][2];
  uint32_t phi[4], plo[4], qml[4], qmh[4];
#pragma unroll
  for (int h = 0; h < 4; h++) {
    const int f = h == 0 ? 0 : h == 1 ? 3 : h == 2 ? 5 : 8, hf = h < 2 ? 2 : 7;
    const bool mine = (h & 1) ? t >= 2 : t < 2;
    qml[h] = mine ? qlo[hf] : 0u;
    qmh[h] = mine ? qhi[hf] : 0u;
    float a[4] = {0.f, 0.f, 0.f, 0.f}, c[4] = {0.f, 0.f, 0.f, 0.f};
    mma16816(a, qlo[f], qhi[f], qlo[f + 1], qhi[f + 1], klo[f], klo[f + 1]);
    mma16816(c, qlo[f], qhi[f], qlo[f + 1], qhi[f + 1], khi[f], khi[f + 1]);
    mma1688(a, qml[h], qmh[h], klo[hf]);
    mma1688(c, qml[h], qmh[h], khi[hf]);
    slo[h][0] = a[0];
    slo[h][1] = a[1];
    shi[h][0] = lg[h & 1][0] = far0 ? a[2] : c[2];
    shi[h][1] = lg[h & 1][1] = far1 ? a[3] : c[3];
    if (!ATT_MERGE && (h & 1)) softmax_two(lg, phi[h - 1], phi[h]);
  }
  TSIF(par == 0 && w == 1, 65);
  if (ATT_GATE == 3 && lane == 0) mbar_arrive(sb + OFF_BAR + 8 * B_ATT2 + (phi[3] & zero));
  wg_sync(1 + par);
  TSIF(par == 0 && w == 1, 66);
  const bool nohist = (w == 0) && (b < 8);
  const uint4* hp = g_halo + ((b - 8) * 2 + par) * 224 + lane;
  uint32_t tg[7];
  if (w > 0) {
    const uint4 v0 = lds128(xa + (w - 1) * 2560), v1 = lds128(xa + (w - 1) * 2560 + 512), v2 = lds128(xa + (w - 1) * 2560 + 1024);
    const uint4 v3 = lds128(xa + (w - 1) * 2560 + 1536), v4 = lds128(xa + (w - 1) * 2560 + 2048);
    kpv[0] = v0.x; kpv[1] = v0.y; kpv[2] = v0.z; kpv[3] = v0.w; kpv[4] = v1.x; kpv[5] = v1.y; kpv[6] = v1.z; kpv[7] = v1.w;
    kpv[8] = v2.x; kpv[9] = v2.y; vpv[0] = v2.z; vpv[1] = v2.w; vpv[2] = v3.x; vpv[3] = v3.y; vpv[4] = v3.z; vpv[5] = v3.w;
    vpv[6] = v4.x; vpv[7] = v4.y; vpv[8] = v4.z; vpv[9] = v4.w;
  } else if (nohist) {
#pragma unroll
    for (int j = 0; j < 10; j++) kpv[j] = vpv[j] = 0u;
  } else {
    TSIF(par == 0, 77);
    halo_read(kpv, vpv, tg, hp);
  }
  if (w == 0 && !nohist) {
    int spins = 0;
    while (true) {
      bool ok = true;
#pragma unroll
      for (int j = 0; j < 7; j++) ok = ok && tg[j] == tag;
      if (__all_sync(0xffffffffu, ok) || ++spins > SPIN_LIMIT) break;
      halo_read(kpv, vpv, tg, hp);
    }
    TSIF(par == 0, 79);
  }
#pragma unroll
  for (int h = 0; h < 4; h++) {
    const int f = h == 0 ? 0 : h == 1 ? 3 : h == 2 ? 5 : 8, hf = h < 2 ? 2 : 7;
    float a[4] = {0.f, 0.f, 0.f, 0.f};
    mma16816(a, qlo[f], qhi[f], qlo[f + 1], qhi[f + 1], kpv[f], kpv[f + 1]);
    mma1688(a, qml[h], qmh[h], kpv[hf]);
    const float ninf = __int_as_float(0xff800000);
    lg[h & 1][0] = far0 ? (nohist ? ninf : a[0]) : slo[h][0];
    lg[h & 1][1] = far1 ? (nohist ? ninf : a[1]) : slo[h][1];
    if (h & 1) {
      softmax_two(lg, plo[h - 1], plo[h]);
      if (ATT_MERGE) {
        const float lh[2][2] = {{shi[h - 1][0], shi[h - 1][1]}, {shi[h][0], shi[h][1]}};
        softmax_two(lh, phi[h - 1], phi[h]);
      }
    }
  }
  TSIF(par == 0 && w <= 1, 67 + w);
  if (ATT_GATE == 2 && lane == 0) mbar_arrive(sb + OFF_BAR + 8 * B_ATT2 + (plo[3] & zero));
  uint32_t ov[20];
#pragma unroll
  for (int hp = 0; hp < 2; hp++) {
    const int hf = hp ? 7 : 2;
    float sh[4] = {0.f, 0.f, 0.f, 0.f}, i0 = 0.f, i1 = 0.f;
#pragma unroll
    for (int e = 0; e < 2; e++) {
      const int h = 2 * hp + e, f = h == 0 ? 0 : h == 1 ? 3 : h == 2 ? 5 : 8;
      const uint32_t a0 = plo[h] & mfar, a2 = plo[h] & ~mfar, a3 = phi[h] & mfar, c1 = phi[h] & ~mfar;
      float sum[4] = {0.f, 0.f, 0.f, 0.f};
      mma1688(sum, plo[h], phi[h], 0x3F803F80u);
      const float r0 = rcp(sum[0]), r1 = rcp(sum[2]);
#pragma unroll
      for (int j = f; j < f + 2; j++) {
        float o[4] = {0.f, 0.f, 0.f, 0.f};
        mma16816(o, a0, 0u, a2, a3, vpv[j], vlo[j]);
        mma1688(o, 0u, c1, vhi[j]);
        ov[2 * j] = pack2(o[0] * r0, o[1] * r0);
        ov[2 * j + 1] = pack2(o[2] * r1, o[3] * r1);
      }
      const bool mine = e ? g >= 4 : g < 4;
      mma16816(sh, a0, 0u, a2, a3, mine ? vpv[hf] : 0u, mine ? vlo[hf] : 0u);
      mma1688(sh, 0u, c1, mine ? vhi[hf] : 0u);
      if (e == 0 || t >= 2) {
        i0 = r0;
        i1 = r1;
      }
    }
    ov[2 * hf] = pack2(sh[0] * i0, sh[1] * i0);
    ov[2 * hf + 1] = pack2(sh[2] * i1, sh[3] * i1);
  }
  if (ATT_GATE == 4 && lane == 0) mbar_arrive(sb + OFF_BAR + 8 * B_ATT2 + (ov[19] & zero));
  TS(32 + 4 * par + w);
  mbar_wait(sb + OFF_BAR + 8 * B_P1, 0);
  const uint32_t oa = sb + OFF_OA + (lane >> 4) * 2048 + (32 * w + 2 * (lane & 15) + par) * 16;
#pragma unroll
  for (int j = 0; j < 5; j++) stsm4(oa + 4096 * j, ov + 4 * j);
  TSIF(par == 0 && w == 0, 120);
  fence_async_smem();
  TSIF(par == 0 && w == 0, 121);
  __syncwarp();
  if (lane == 0) mbar_arrive(sb + OFF_BAR + 8 * B_ATTN);
  TSM(w == 0 || w == 2, 122 + par + (w == 2 ? 3 : 0));
}

struct Maps {
  CUtensorMap x, wm, wt, k, v, y, wo, qm, qt, om, ot, u;
};

__device__ __forceinline__ void load_stage(uint32_t sb, int kb, int b, const Maps& m) {
  const uint32_t st = sb + (kb & 3) * STAGE_BYTES, bar = sb + OFF_BAR + 8 * (B_FULL1 + (kb & 3));
  const int r = b >> 3, hg = b & 7, slab = kb - KV_KB;
  const bool kv = slab >= 0 && slab < 5;
  const uint32_t kbar = sb + OFF_BAR + 8 * (B_KV + slab), dst = sb + OFF_KVS + slab * KVS_BYTES;
  mbar_expect_tx(bar, STAGE_BYTES);
  if (kv) mbar_expect_tx(kbar, KVS_BYTES);
  tma_3d(st, &m.x, 64 * kb, 64 * r, 0, bar);
  if (kv && KV_MIX) tma_3d(dst, &m.k, 0, 32 * (b >> 1) - 3, 2 * slab + (b & 1), kbar);
  tma_3d(st + ST_W, &m.wm, 80 * hg + (tail_first(hg) ? 16 : 0), 64 * kb, 0, bar);
  if (kv && KV_MIX) tma_3d(dst + KVS_V, &m.v, 0, 32 * (b >> 1), 2 * slab + (b & 1), kbar);
  tma_3d(st + ST_WT, &m.wt, 80 * hg + (tail_first(hg) ? 0 : 64), 64 * kb, 0, bar);
  if (kv && !KV_MIX) tma_3d(dst, &m.k, 0, 32 * (b >> 1) - 3, 2 * slab + (b & 1), kbar);
  if (kv && !KV_MIX) tma_3d(dst + KVS_V, &m.v, 0, 32 * (b >> 1), 2 * slab + (b & 1), kbar);
}

__global__ void __launch_bounds__(NTHR, 1) fused_kernel(const __grid_constant__ Maps m, const Params p) {
  extern __shared__ __align__(1024) uint8_t smem[];
  const uint32_t sb = (uint32_t)__cvta_generic_to_shared(smem);
  const uint32_t bars = sb + OFF_BAR;
  const int tid = threadIdx.x, lane = tid & 31;
  int b = blockIdx.x;
  if (BMAP == 1) b = (((b & 63) >> 3) * 2 + (b & 1)) * 8 + (((b < 64 ? 0x6521 : 0x7430) >> (4 * ((b >> 1) & 3))) & 7);
  if (BMAP == 2) b = ((b & 63) >> 2) * 8 + (((b < 64 ? 0x6521 : 0x7430) >> (4 * (b & 3))) & 7);
  if (BMAP == 3) b = (((b & 63) >> 3) * 2 + (b & 1)) * 8 + (((b < 64 ? 0x7430 : 0x6521) >> (4 * ((b >> 1) & 3))) & 7);
  if (BMAP == 4) b = (((b >> 4) * 2 + (b & 1)) * 8) + ((b >> 1) & 7);
  if (BMAP == 5) b = 127 - b;
  const int r = b >> 3, hg = b & 7;

  if (tid == T_ISSUE) {
    TSM(true, 0);
#pragma unroll
    for (int i = 0; i < 4; i++) mbar_init(bars + 8 * (B_FULL1 + i), 1);
#pragma unroll
    for (int i = 0; i < 3; i++) mbar_init(bars + 8 * (B_KV + i), 1);
    fence_async_smem();
#pragma unroll 1
    for (int kb = 0; kb <= PRE2; kb++) load_stage(sb, kb, b, m);
  } else if (tid >= T_PF && tid < T_PF + 12) {
    tm_prefetch(&m.x + (tid - T_PF));
  } else if (tid == T_INIT) {
#pragma unroll
    for (int i = 0; i < 4; i++) mbar_init(bars + 8 * (B_EMPTY1 + i), 8);
#pragma unroll
    for (int i = 0; i < 8; i++) mbar_init(bars + 8 * (B_FULL2 + i), 1);
#pragma unroll
    for (int i = 0; i < 4; i++) mbar_init(bars + 8 * (B_EMPTY2 + i), 8);
#pragma unroll
    for (int i = 0; i < 4; i++) mbar_init(bars + 8 * (B_U + i), 1);
    mbar_init(bars + 8 * B_HA, 4);
    mbar_init(bars + 8 * B_GATE, 4);
    mbar_init(bars + 8 * B_HB, 1);
    mbar_init(bars + 8 * B_KVD, 4);
    mbar_init(bars + 8 * B_QF, 1);
    mbar_init(bars + 8 * B_ATTN, 8);
    mbar_init(bars + 8 * B_ATT2, 8);
    mbar_init(bars + 8 * B_P1, 8);
    mbar_init(bars + 8 * B_C34, 1);
    mbar_init(bars + 8 * B_YRB, 1);
#pragma unroll
    for (int i = 0; i < 5; i++) mbar_init(bars + 8 * (B_YST + i), 4);
#pragma unroll
    for (int i = 0; i < 5; i++) mbar_init(bars + 8 * (B_US + i), U_TMA ? 4 : 1);
    mbar_init(bars + 8 * B_YSIG, 1);
    mbar_init(bars + 8 * B_YFULL, 1);
    mbar_init(bars + 8 * B_EPOCH, 1);
    mbar_init(bars + 8 * B_PREP, 4);
    mbar_init(bars + 8 * B_USIG, 1);
    mbar_init(bars + 8 * B_WST, 1);
#pragma unroll
    for (int i = 3; i < 5; i++) mbar_init(bars + 8 * (B_KV + i), 1);
    mbar_init(bars + 8 * B_E3, 8);
    mbar_init(bars + 8 * B_LAST, 1);
    mbar_init(bars + 8 * B_OSIG, 1);
    mbar_init(bars + 8 * B_WOP, 1);
    fence_async_smem();
  }
  const int warp = __shfl_sync(0xffffffffu, tid >> 5, 0), wg = warp >> 2, w = warp & 3;
  __syncthreads();

  if (wg == 3) {
    asm volatile("setmaxnreg.dec.sync.aligned.u32 56;");
    if (w == 0) {
      if (lane == 0) {
#pragma unroll 1
        for (int kb = 1 + PRE2; kb < 10; kb++) {
          if (kb >= 4) mbar_wait(bars + 8 * (kb == 7 ? B_E3 : B_EMPTY1 + (kb & 3)), (kb >> 3) & 1);
          TSIF(kb >= 4, 44 + kb);
          load_stage(sb, kb, b, m);
          TSIF(kb == 3, 60);
          if (kb == TRIG_KB) mbar_arrive(bars + 8 * B_LAST);
        }
        mbar_wait(bars + 8 * B_WOP, 0);
        mbar_wait(bars + 8 * WL_TRIG, 0);
        mbar_wait(bars + 8 * B_EPOCH, 0);
        flag_wait(g_cnt + C_W + 32 * hg, (lds32(sb + OFF_EPOCH) + 1) * 16);
        TS(30);
#pragma unroll 1
        for (int j = 0; j < 8; j++) {
          if (j >= 6) mbar_wait(bars + 8 * (B_EMPTY2 + j - 6), 0);
          if (j == 4) mbar_wait(bars + 8 * B_ATTN, 0);
          TSIF(j >= 6, 100 + j);
          if (RF_GATE && j == 6) mbar_wait(bars + 8 * B_YSIG, 0);
          mbar_expect_tx(bars + 8 * (B_FULL2 + j), j == 0 ? WO_BYTES : j == 5 ? O_BYTES + WO_BYTES + 512 : O_BYTES + WO_BYTES);
          bulk_load(sb + off_w(j), g_WO + (hg * 8 + step_src(hg, j)) * 800, WO_BYTES, bars + 8 * (B_FULL2 + j));
        }
        mbar_wait(bars + 8 * (B_EMPTY2 + 3), 0);
        mbar_expect_tx(bars + 8 * B_QF, O_BYTES);
        tma_2d(sb + OFF_QS, &m.qm, 80 * hg, 128 * r, bars + 8 * B_QF);
        tma_2d(sb + OFF_QT, &m.qt, 80 * hg + 64, 128 * r, bars + 8 * B_QF);
      }
    } else if (w == 1) {
      unsigned epoch = 0;
      if (lane == 0) {
        epoch = atomicAdd(g_cnt + C_LAUNCH, 1u) / NCTA;
        asm volatile("st.shared.u32 [%0], %1;" ::"r"(sb + OFF_EPOCH), "r"(epoch) : "memory");
        mbar_arrive(bars + 8 * B_EPOCH);
        mbar_wait(bars + 8 * B_KVD, 0);
        mbar_expect_tx(bars + 8 * B_HB, 5 * 4096);
#pragma unroll 1
        for (int c = 0; c < 5; c++) {
          if (c == 3) mbar_wait(bars + 8 * B_S3, 0);
          bulk_load(sb + off_ch(c) + U_BYTES, p.ssm_k + (5 * b + c) * SEQ, 4096, bars + 8 * B_HB);
        }
#pragma unroll
        for (int c = 0; c < 4; c++) mbar_expect_tx(bars + 8 * (B_U + c), c < 3 ? U_BYTES : 2 * U_BYTES);
        const uint4* usrc = g_U + 5 * b * U_PITCH;
        mbar_wait(bars + 8 * B_USIG, 0);
        flag_wait(g_cnt + C_PREP + 32 * (b & 15), (epoch + 1) * NCTA);
        TS(23);
#pragma unroll
        for (int c = 0; c < 5; c++) {
          if (c == 3 && U_TRIM) mbar_wait(bars + 8 * (B_U + 2), 0);
          bulk_load(sb + off_ch(c), usrc + c * U_PITCH, U_BYTES, bars + 8 * (B_U + (c < 3 ? c : 3)));
          TSIF(c == 0 || c == 4, 116 + (c >> 2));
        }
      }
      epoch = __shfl_sync(0xffffffffu, epoch, 0);
      if (lane < 8) {
        const int src = (b & ~7) | step_src(hg, lane);
        mbar_wait(bars + 8 * OP_TRIG, 0);
        TS(20);
        bool seen = false;
#pragma unroll 1
        for (int spins = 0; spins < SPIN_LIMIT; spins++) {
          const bool now = !seen && (int)(flag_read(g_cnt + C_O + 32 * src) - (epoch + 1)) >= 0;
          if (now && lane >= 1 && lane < 4) bulk_load(sb + off_o(lane), g_O + src * 1280, O_BYTES, bars + 8 * (B_FULL2 + lane));
          seen = seen || now;
          if (__all_sync(0xff, seen)) break;
        }
        TS(21);
        if (lane == 5) bulk_load(sb + OFF_GATE, g_gate + 128 * r, 512, bars + 8 * (B_FULL2 + 5));
#pragma unroll 1
        for (int j = 4; j < 8; j++) {
          if (lane == j) {
            mbar_wait(bars + 8 * (j < 6 ? B_C34 : B_EMPTY2 + j - 6), 0);
            if (RF_GATE && j == 6) mbar_wait(bars + 8 * B_YSIG, 0);
            bulk_load(sb + off_o(j), g_O + src * 1280, O_BYTES, bars + 8 * (B_FULL2 + j));
          }
          __syncwarp(0xff);
        }
        TS(22);
      }
    } else if (w == 2) {
      mbar_wait(bars + 8 * B_PREP, 0);
      flag_signal(g_cnt + C_PREP, 16, lane);
      TS(25);
      if (lane == 0) mbar_arrive(bars + 8 * B_USIG);
      mbar_wait(bars + 8 * B_GATE, 0);
      if (((NOMB & 1) || O_RB) && lane == 0) asm volatile("fence.release.gpu;" ::: "memory");
      mbar_wait(bars + 8 * B_ATTN, 0);
      if (lane == 0) {
        if (O_DEFER) mbar_wait(bars + 8 * (B_U + 3), 0);
        asm volatile("cp.async.bulk.global.shared::cta.bulk_group [%0], [%1], 20480;\ncp.async.bulk.commit_group;"
                     ::"l"(g_O + b * 1280), "r"(sb + OFF_OA) : "memory");
        if (O_RB == 2) {
          asm volatile("cp.async.bulk.wait_group.read 0;" ::: "memory");
          mbar_expect_tx(bars + 8 * B_ORB, O_BYTES);
          bulk_load(sb + OFF_OA, g_O + b * 1280, O_BYTES, bars + 8 * B_ORB);
          mbar_wait(bars + 8 * B_ORB, 0);
          flag_bump(g_cnt + C_O + 32 * b);
        } else if (O_RB) asm volatile("cp.async.bulk.wait_group.read 0;" ::: "memory");
        else asm volatile("cp.async.bulk.wait_group 0;\nfence.proxy.async.global;" ::: "memory");
      }
      TS(74);
      if (O_RB == 2) {
      } else if (O_RB) {
        __syncwarp();
        unsigned v[5];
#pragma unroll
        for (int c = 0; c < 5; c++) v[c] = flag_read(reinterpret_cast<const unsigned*>(g_O + b * 1280 + 256 * c + 8 * lane + 7));
        const unsigned dep = __reduce_or_sync(0xffffffffu, (v[0] ^ v[1] ^ v[2] ^ v[3] ^ v[4]) & p.zero);
        if (lane == 0) flag_bump(g_cnt + C_O + 32 * b + dep);
      } else if (!(NOMB & 1)) flag_signal(g_cnt + C_O + 32 * b, 1, lane);
      else if (lane == 0) flag_bump(g_cnt + C_O + 32 * b);
      TS(26);
      if (lane == 0) mbar_arrive(bars + 8 * B_OSIG);

    } else {
      if (lane == 0) {
        uint4* dst = g_WO + (hg * 8 + (r >> 1)) * 800 + (r & 1) * 80;
        mbar_wait(bars + 8 * B_P1, 0);
        mbar_wait(bars + 8 * WB_TRIG, 0);
        mbar_expect_tx(bars + 8 * B_WST, WO_BYTES / 2);
        tma_3d(sb + OFF_WS, &m.wo, 0, 40 * r, 5 * hg, bars + 8 * B_WST);
        mbar_wait(bars + 8 * B_WST, 0);
        mbar_wait(bars + 8 * WO_TRIG, 0);
#pragma unroll 1
        for (int n = 0; n < 5; n++)
          asm volatile("cp.async.bulk.global.shared::cta.bulk_group [%0], [%1], 1280;" ::"l"(dst + 160 * n), "r"(sb + OFF_WS + 1280 * n) : "memory");
        asm volatile("cp.async.bulk.commit_group;\ncp.async.bulk.wait_group 0;\nfence.proxy.async.global;" ::: "memory");
        if (!(NOMB & 4)) asm volatile("fence.release.gpu;" ::: "memory");
        flag_bump(g_cnt + C_W + 32 * hg);
        mbar_arrive(bars + 8 * B_WOP);
        TS(71);
        mbar_expect_tx(bars + 8 * B_C34, 3 * U_BYTES);
        mbar_expect_tx(bars + 8 * B_YRB, 2 * U_BYTES);
#pragma unroll 1
        for (int c = 0; c < 5; c++) {
          mbar_wait(bars + 8 * (B_YST + c), 0);
          asm volatile("cp.async.bulk.global.shared::cta.bulk_group [%0], [%1], 4096;\ncp.async.bulk.commit_group;\n"
                       "cp.async.bulk.wait_group.read 0;" ::"l"(g_Y + (5 * b + c) * Y_PITCH), "r"(sb + off_ch(c)) : "memory");
          bulk_load(sb + off_ch(c), g_Y + (5 * b + c) * Y_PITCH, U_BYTES, bars + 8 * (c < 3 ? B_C34 : B_YRB));
        }
        TS(75);
        mbar_wait(bars + 8 * B_C34, 0);
        mbar_wait(bars + 8 * B_YRB, 0);
        flag_bump(g_cnt + C_Y + 32 * (b >> 4));
        TS(27);
        mbar_arrive(bars + 8 * B_YSIG);
        mbar_expect_tx(bars + 8 * B_YFULL, 20480);
        flag_wait(g_cnt + C_Y + 32 * hg, (lds32(sb + OFF_EPOCH) + 1) * 16);
        TS(24);
        tma_2d(sb + OFF_YT, &m.y, 128 * r, 80 * hg, bars + 8 * B_YFULL);
        tma_2d(sb + OFF_YT + 10240, &m.y, 128 * r + 64, 80 * hg, bars + 8 * B_YFULL);
      }
    }
  } else {
    asm volatile("setmaxnreg.inc.sync.aligned.u32 152;");
    if (wg < 2) {
      float acc[120];
#pragma unroll
      for (int i = 0; i < 120; i++) acc[i] = 0.f;
      const uint32_t da = desc_lo(sb + wg * 8192, 16), db = desc_lo(sb + ST_W, 8192), dc = desc_lo(sb + ST_WT, 2048);
      if (PW1) pin<120>(acc);
      if (PW1 == 2) mbar_wait(bars + 8 * B_FULL1, 0);
#pragma unroll 1
      for (int kb = 0; kb < 10; kb++) {
        mbar_wait(bars + 8 * (B_FULL1 + (kb & 3)), (kb >> 2) & 1);
        const uint32_t so = (kb & 3) * (STAGE_BYTES >> 4);
        wg_fence();
#pragma unroll
        for (int k = 0; k < 4; k++) {
          WgSST<192>::mma<HI_SW128, HI_SW128>(acc, da + so + 2 * k, db + so + 128 * k, 1);
          WgSST<48>::mma<HI_SW128, HI_SW32>(acc + 96, da + so + 2 * k, dc + so + 32 * k, 1);
        }
        wg_commit();
        wg_wait<1>();
        if (kb > 0 && lane == 0) mbar_arrive(bars + 8 * (kb == 4 ? B_E3 : B_EMPTY1 + ((kb - 1) & 3)));
      }
      mbar_wait(bars + 8 * B_EPOCH, 0);
      const uint32_t tag = lds32(sb + OFF_EPOCH) + 1;
      mbar_wait(bars + 8 * B_S3, 0);
      wg_wait<0>();
      pin<120>(acc);
      if (lane == 0) mbar_arrive(bars + 8 * B_P1);
      TSM(w == 0, 3 + wg);
      attention(acc, sb, b, wg, w, lane, tag, p.zero);
    } else {
      const int tw = tid & 127, chl = 64 * (b & 1) + 8 * w + (lane >> 2);
      uint4* up = g_U + chl * U_PITCH + ((4 * (b >> 1) + (lane & 3)) ^ ((b >> 2) & 1));
      uint2 sw[10];
      uint32_t dv = 0;
      if (lane < 5) dv = __ldg(reinterpret_cast<const unsigned short*>(p.ssm_D) + 5 * b + lane);
#pragma unroll
      for (int i = 0; i < 10; i++) sw[i] = ldg64(reinterpret_cast<const uint2*>(p.shift_k) + chl + 128 * (i >> 1) + 32 * (i & 1));
      uint32_t tab[12];
      uint32_t tt[2];
      fft_tables(tab, tw);
      fft_twiddles(tt, tw);
      uint4 res[10];
#pragma unroll
      for (int i = 0; i < 10; i++) res[i] = make_uint4(0, 0, 0, 0);
#pragma unroll 1
      for (int slab = 0; slab < 5; slab++) {
#pragma unroll
        for (int i = 0; i < 8; i++) res[i] = res[i + 2];
        prep_slab(res + 8, sw, sb, slab, w, lane);
        TSIF(w == 0, 99 + 4 * slab);
#pragma unroll
        for (int i = 0; i < 8; i++) sw[i] = sw[i + 2];
      }
      TSIF(w == 0, 28);
      __syncwarp();
      if (lane == 0) mbar_arrive(bars + 8 * B_KVD + ((res[8].x ^ res[9].x) & p.zero));
      mbar_wait(bars + 8 * B_KVD, 0);
      fft_tables_store(tab, sb, tw);
      mbar_wait(bars + 8 * B_LAST, 0);
#pragma unroll
      for (int i = 0; i < 10; i++) up[(128 * (i >> 1) + 32 * (i & 1)) * U_PITCH] = res[i];
      __syncwarp();
      if (lane == 0) mbar_arrive(bars + 8 * B_PREP);
      TSIF(w == 0 && !U_TMA, 5);
      mbar_wait(bars + 8 * (G_AFTER ? B_USIG : B_LAST), 0);
      prep_gate(p, b, w, lane);
      __syncwarp();
      if (lane == 0) mbar_arrive(bars + 8 * B_GATE);
      TSIF(w == 0, 72);
      mbar_wait(bars + 8 * B_HB, 0);
      TSIF(w == 0, 2);
      const uint32_t ha = sb + U_BYTES + ((tw >> 3) * 16 + 8 + (tw & 7)) * 16;
      uint4 hv[5];
#pragma unroll
      for (int c = 0; c < 5; c++) hv[c] = lds128(ha + off_ch(c));
      __syncwarp();
#pragma unroll
      for (int c = 0; c < 5; c++) sts128((ha ^ 16) + off_ch(c), hv[c].x, hv[c].y, hv[c].z, hv[c].w);
      asm volatile("st.shared.v2.u32 [%0], {%1, %2};" ::"r"(sb + OFF_TT + 8 * tw), "r"(tt[0]), "r"(tt[1]) : "memory");
      if (tw < 5) asm volatile("st.shared.f32 [%0], %1;" ::"r"(sb + OFF_D + 4 * tw), "f"(bf_lo(dv) * 0.125f) : "memory");
      fence_async_smem();
      __syncwarp();
      if (lane == 0) mbar_arrive(bars + 8 * B_HA);
      TSIF(w == 0, 6);
    }

    FftConst fc;
    TSM(w == 0 && wg == 0, 104);
    mbar_wait(bars + 8 * B_HA, 0);
    fft_matrices(fc, sb, w, lane);
    TSM(w == 0 && wg == 0, 105);
    TSM(w == 0 && wg == 2, 124);
#pragma unroll 1
    for (uint32_t tasks = wg == 0 ? TASK0 : wg == 1 ? TASK1 : TASK2; tasks; tasks >>= 4) {
      const int c = (tasks & 7) - 1;
      conv_channel(fc, sb, c, wg, w, lane);
      if (lane == 0) mbar_arrive(bars + 8 * (B_YST + c));
      TSM(w == 0, 10 + c);
    }

    if (wg < 2) {
      const int g = lane >> 2;
      float acc[40];
#pragma unroll
      for (int i = 0; i < 40; i++) acc[i] = 0.f;
      const uint32_t da = desc_lo(sb + wg * 1024, 2048), db = desc_lo(sb, 2560);
      if (!WO_FAST) mbar_wait(bars + 8 * (O_RB == 2 ? B_ORB : B_ATTN), 0);
      mbar_wait(bars + 8 * (B_YST + 3), 0);
      mbar_wait(bars + 8 * (B_YST + 4), 0);
      if (PW2 && !WO_FAST) mbar_wait(bars + 8 * B_FULL2, 0);
      TSM(w == 0, 15 + wg);
#pragma unroll 1
      for (int j = 0; j < 8; j++) {
        mbar_wait(bars + 8 * (B_FULL2 + j), 0);
        const uint32_t oa = da + (off_o(j) >> 4), ob = db + (off_w(j) >> 4);
        wg_fence();
#pragma unroll
        for (int k = 0; k < 5; k++) WgSST<80>::mma<HI_NONE, HI_SW32>(acc, oa + 256 * k, ob + 32 * k, 1);
        wg_commit();
        wg_wait<1>();
        if (j >= 1 && j <= 4 && lane == 0) mbar_arrive(bars + 8 * (B_EMPTY2 + j - 1));
      }
      TSIF(w == 0 && wg == 0, 113);
      const int tr = 64 * wg + 16 * w + (lane & 15);
      const uint32_t fm = sb + OFF_QS + tr * 128, fx = (lane >> 4) ^ (tr & 7);
      const uint32_t ft = sb + OFF_QT + tr * 32 + (((lane >> 4) ^ (tr >> 2)) & 1) * 16;
      const float g0 = __uint_as_float(lds32(sb + OFF_GATE + (64 * wg + 16 * w + g) * 4));
      const float g1 = __uint_as_float(lds32(sb + OFF_GATE + (64 * wg + 16 * w + 8 + g) * 4));
      const uint32_t ga = pack2(g0, g0), gb = pack2(g1, g1);
      const uint32_t na = pack2(1.f - g0, 1.f - g0), nb = pack2(1.f - g1, 1.f - g1);

      uint32_t qf[20];
      mbar_wait(bars + 8 * B_QF, 0);
#pragma unroll
      for (int j = 0; j < 5; j++) ldsm4(qf + 4 * j, j < 4 ? fm + ((fx ^ (2 * j)) << 4) : ft);
      if (FUSE_MIX) {
#pragma unroll
        for (int i = 0; i < 20; i++) {
          qf[i] = bmul((i & 1) ? gb : ga, qf[i]);
          asm volatile("" : "+r"(qf[i]));
        }
      }
      wg_wait<0>();
      pin<40>(acc);
      TSM(w == 0, 17 + wg);
      uint32_t pb[20];
#pragma unroll
      for (int j = 0; j < 10; j++) {
        pb[2 * j] = bmul(na, pack2(acc[4 * j], acc[4 * j + 1]));
        pb[2 * j + 1] = bmul(nb, pack2(acc[4 * j + 2], acc[4 * j + 3]));
        asm volatile("" : "+r"(pb[2 * j]), "+r"(pb[2 * j + 1]));
      }
      const uint32_t ya = sb + OFF_YT + wg * 10240 + ((lane >> 4) * 8 + (lane & 7)) * 128 +
                          (((2 * w + (((lane >> 3) & 1) ^ wg)) ^ (lane & 7)) << 4);
      mbar_wait(bars + 8 * B_YFULL, 0);
      TSM(w == 0 && wg == 0, 19);
#pragma unroll
      for (int j = 0; j < 5; j++) {
        uint32_t y[4];
        ldsm4t(y, ya + 2048 * j);
#pragma unroll
        for (int i = 0; i < 4; i++)
          qf[4 * j + i] = FUSE_MIX ? bfma(qf[4 * j + i], y[i], pb[4 * j + i]) : badd(bmul((i & 1) ? gb : ga, bmul(qf[4 * j + i], y[i])), pb[4 * j + i]);
      }
#pragma unroll
      for (int j = 0; j < 5; j++) stsm4(j < 4 ? fm + ((fx ^ (2 * j)) << 4) : ft, qf + 4 * j);
      fence_async_smem();
      __syncwarp();
      if (lane == 0) {
        const int row = 64 * wg + 16 * w;
        asm volatile("cp.async.bulk.tensor.2d.global.shared::cta.bulk_group [%0, {%2, %3}], [%1];"
                     ::"l"(&m.om), "r"(sb + OFF_QS + row * 128), "r"(80 * hg), "r"(128 * r + row) : "memory");
        asm volatile("cp.async.bulk.tensor.2d.global.shared::cta.bulk_group [%0, {%2, %3}], [%1];"
                     ::"l"(&m.ot), "r"(sb + OFF_QT + row * 32), "r"(80 * hg + 64), "r"(128 * r + row) : "memory");
        asm volatile("cp.async.bulk.commit_group;\ncp.async.bulk.wait_group.read 0;" ::: "memory");
      }
      TSM(true, 40 + 4 * wg + w);
      if (ENDBAR) asm volatile("bar.sync 15, 256;" ::: "memory");
    }
  }
}

typedef CUresult (*EncodeFn)(CUtensorMap*, CUtensorMapDataType, cuuint32_t, void*, const cuuint64_t*, const cuuint64_t*,
                             const cuuint32_t*, const cuuint32_t*, CUtensorMapInterleave, CUtensorMapSwizzle,
                             CUtensorMapL2promotion, CUtensorMapFloatOOBfill);

void encode(EncodeFn fn, CUtensorMap* tm, const void* base, int rank, const cuuint64_t* dims, const cuuint64_t* strides,
            const cuuint32_t* box, CUtensorMapSwizzle swz) {
  const cuuint32_t ones[3] = {1, 1, 1};
  fn(tm, CU_TENSOR_MAP_DATA_TYPE_BFLOAT16, rank, const_cast<void*>(base), dims, strides, box, ones,
     CU_TENSOR_MAP_INTERLEAVE_NONE, swz, CU_TENSOR_MAP_L2_PROMOTION_L2_128B, CU_TENSOR_MAP_FLOAT_OOB_FILL_NONE);
}

}

extern "C" void kernel_launch(void* const* d_in, const int* in_sizes, int n_in, void* d_out, int out_size) {
  (void)in_sizes; (void)n_in; (void)out_size;
  Params p;
  p.q = (const __nv_bfloat16*)d_in[0];
  p.k = (const __nv_bfloat16*)d_in[1];
  p.v = (const __nv_bfloat16*)d_in[2];
  p.shift_k = (const __nv_bfloat16*)d_in[3];
  p.ssm_k = (const __nv_bfloat16*)d_in[4];
  p.ssm_D = (const __nv_bfloat16*)d_in[5];
  p.wqkv = (const __nv_bfloat16*)d_in[7];
  p.wo = (const __nv_bfloat16*)d_in[8];
  p.gate_w = (const __nv_bfloat16*)d_in[9];
  p.out = (__nv_bfloat16*)d_out;
  p.zero = 0;

  static EncodeFn fn = nullptr;
  static void *yaddr = nullptr, *uaddr = nullptr;
  if (!fn) {
    cudaDriverEntryPointQueryResult qr;
    void* f = nullptr;
    cudaGetDriverEntryPoint("cuTensorMapEncodeTiled", &f, cudaEnableDefault, &qr);
    fn = (EncodeFn)f;
    cudaGetSymbolAddress(&yaddr, g_Y);
    cudaGetSymbolAddress(&uaddr, g_U);
    cudaFuncSetAttribute(fused_kernel, cudaFuncAttributeMaxDynamicSharedMemorySize, SMEM_BYTES);
  }
  Maps m;
  {
    const cuuint64_t dims[3] = {640, 1024, 2}, st[2] = {2560, 1280};
    const cuuint32_t box[3] = {64, 64, 2};
    encode(fn, &m.x, p.q, 3, dims, st, box, CU_TENSOR_MAP_SWIZZLE_128B);
  }
  {
    const cuuint64_t dims[3] = {640, 640, 3}, st[2] = {3840, 1280};
    const cuuint32_t box[3] = {64, 64, 3}, boxt[3] = {16, 64, 3};
    encode(fn, &m.wm, p.wqkv, 3, dims, st, box, CU_TENSOR_MAP_SWIZZLE_128B);
    encode(fn, &m.wt, p.wqkv, 3, dims, st, boxt, CU_TENSOR_MAP_SWIZZLE_32B);
  }
  {
    const cuuint64_t dims[3] = {64, 2048, 10}, st[2] = {1280, 128};
    const cuuint32_t boxk[3] = {64, 35, 1}, boxv[3] = {64, 32, 1};
    encode(fn, &m.k, p.k, 3, dims, st, boxk, CU_TENSOR_MAP_SWIZZLE_128B);
    encode(fn, &m.v, p.v, 3, dims, st, boxv, CU_TENSOR_MAP_SWIZZLE_128B);
  }
  {
    const cuuint64_t dims[3] = {16, 640, 40}, st[2] = {1280, 32};
    const cuuint32_t box[3] = {16, 40, 5};
    encode(fn, &m.wo, p.wo, 3, dims, st, box, CU_TENSOR_MAP_SWIZZLE_32B);
  }
  {
    const cuuint64_t dims[2] = {2048, 640}, st[1] = {Y_PITCH * 16};
    const cuuint32_t box[2] = {64, 80};
    encode(fn, &m.y, yaddr, 2, dims, st, box, CU_TENSOR_MAP_SWIZZLE_128B);
    const cuuint64_t stu[1] = {U_PITCH * 16};
    const cuuint32_t boxu[2] = {32, 64};
    encode(fn, &m.u, uaddr, 2, dims, stu, boxu, CU_TENSOR_MAP_SWIZZLE_NONE);
  }
  {
    const cuuint64_t dims[2] = {640, 2048}, st[1] = {1280};
    const cuuint32_t bqm[2] = {64, 128}, bqt[2] = {16, 128}, bom[2] = {64, 16}, bot[2] = {16, 16};
    encode(fn, &m.qm, p.q, 2, dims, st, bqm, CU_TENSOR_MAP_SWIZZLE_128B);
    encode(fn, &m.qt, p.q, 2, dims, st, bqt, CU_TENSOR_MAP_SWIZZLE_32B);
    encode(fn, &m.om, p.out, 2, dims, st, bom, CU_TENSOR_MAP_SWIZZLE_128B);
    encode(fn, &m.ot, p.out, 2, dims, st, bot, CU_TENSOR_MAP_SWIZZLE_32B);
  }
  fused_kernel<<<NCTA, NTHR, SMEM_BYTES>>>(m, p);
}
```

```cpp
#include <cuda.h>
#include <cuda_bf16.h>
#include <cuda_runtime.h>
#include <stdint.h>

namespace {

constexpr int SEQ = 2048, DIM = 640, NCTA = 128, NTHR = 512;

#define TRIG_KB 9
#define KV_KB 2
#define DEV_EXIT 0
#define ATT_GATE 0
#define G_AFTER 0
#define FENCE_LO 0
#define FENCE_HI 0
#define PW1 2
#define PW2 1
#define ENDBAR 0
#define PAD_KB 0
#define Y_ALIAS 1
#define NOMB 0
#define SRC_ROT 0
#define WAIT_NS 0
#define WB_TRIG B_USIG
#define G_POS 0
#define TAILF 1
#define T_ISSUE 384
#define T_PF 416
#define T_INIT 448
#define ATT_MERGE 0
#define BMAP 1
#define PRE2 1
#define KV_MIX 0
#define O_DEFER 0
#define TASK0 0x52
#define TASK1 0x3
#define TASK2 0x41
#define HALO_FIRST 1
#define PREV_EARLY 0
#define Y_RB 2
#define O_RB 0
#define O_EAGER 1
#define OP_TRIG B_OSIG
#define FUSE_MIX 1
#define Q_EARLY 1
#define WO_FAST 0
#define U_TRIM 1
#define Q_SLOT 2
#define ACQ 0
#define U_TMA 0
#define U_GATE 0
#define RF_GATE 0
#define WO_TRIG B_WST
#define WL_TRIG B_WOP
#define WO_GATE 1

constexpr uint32_t STAGE_BYTES = 47104, ST_W = 16384, ST_WT = 40960;
constexpr uint32_t O_BYTES = 20480, WO_BYTES = 12800;
constexpr uint32_t OFF_OA = 0;
constexpr uint32_t OFF_QS = Q_SLOT * O_BYTES, OFF_QT = OFF_QS + 16384;
constexpr uint32_t OFF_WC = 81920;
constexpr uint32_t OFF_WA = 94720;
constexpr uint32_t OFF_GATE = 145920;
constexpr uint32_t OFF_TT = 146432;
constexpr uint32_t OFF_KVX = 148480;
constexpr uint32_t OFF_CH3 = 163840;
constexpr uint32_t CH_BYTES = 12288, U_BYTES = 4096;
constexpr uint32_t OFF_FT = 225280, OFF_GT = 229376;
constexpr uint32_t OFF_CH0 = 188416;
constexpr uint32_t OFF_KVS = OFF_CH0, KVS_V = 4480, KVS_BYTES = 8576;
constexpr uint32_t OFF_WS = OFF_WA;
__device__ __forceinline__ uint32_t off_us(int s) { return OFF_CH0 + 4096 * ((0x65320 >> (4 * s)) & 7); }
constexpr uint32_t OFF_YT = 163840;
constexpr uint32_t OFF_BAR = 231936;
constexpr uint32_t SMEM_BYTES = OFF_BAR + 512;

enum : uint32_t {
  B_FULL1 = 0, B_EMPTY1 = 4, B_S3 = 7, B_FULL2 = 52, B_EMPTY2 = 13, B_U = 8, B_GATE = 12, B_HA = 19, B_HB = 20,
  B_ATTN = 21, B_C34 = 22, B_YRB = 23, B_YFULL = 24, B_EPOCH = 25, B_PREP = 26, B_P1 = 27, B_LAST = 28,
  B_E3 = 29, B_OSIG = 30, B_WOP = 31, B_USIG = 32, B_WST = 33, B_KV = 34, B_KVD = 39, B_QF = 17, B_ATT2 = 18, B_YST = 40,
  B_ORB = 45, B_US = 45, B_YSIG = 50
};
constexpr uint32_t OFF_EPOCH = OFF_BAR + 8 * 51, OFF_D = OFF_BAR + 8 * 60;
__device__ __forceinline__ uint32_t off_o(int j) { return j < 4 ? OFF_OA + j * O_BYTES : j < 6 ? OFF_CH0 + (j - 4) * O_BYTES : OFF_OA + (j - 6) * O_BYTES; }
__device__ __forceinline__ uint32_t off_w(int j) { return j < 4 ? OFF_WA + j * WO_BYTES : j == 4 ? OFF_KVX : j == 5 ? OFF_WC : OFF_WA + (j - 6) * WO_BYTES; }
__device__ __forceinline__ int step_src(int hg, int j) {
  if (SRC_ROT == 2) {
    const int pos = (0x37621540 >> (4 * hg)) & 7;
    return j == 0 ? hg : (0x65217430 >> (4 * (j <= pos ? j - 1 : j))) & 7;
  }
  return SRC_ROT ? (hg + j) & 7 : j == 0 ? hg : j <= hg ? j - 1 : j;
}
__device__ __forceinline__ bool tail_first(int hg) { return TAILF && (hg & 3) == 3; }
__device__ __forceinline__ uint32_t off_ch(int c) { return (c < 3 ? OFF_CH0 : OFF_CH3 - 3 * CH_BYTES) + c * CH_BYTES; }

#define U_PITCH 264
__device__ __align__(1024) uint4 g_U[DIM * U_PITCH];
__device__ uint4 g_O[NCTA * 1280];
#define g_Y g_U
constexpr int Y_PITCH = U_PITCH;
__device__ uint4 g_WO[64 * 800];
__device__ uint4 g_halo[NCTA * 2 * 7 * 32];
__device__ float g_gate[SEQ + PAD_KB * 256];
__device__ unsigned g_cnt[32 * (1 + 2 * 16 + 8 + NCTA)];
constexpr int C_LAUNCH = 0, C_PREP = 32, C_Y = 32 * 17, C_W = 32 * 33, C_O = 32 * 41;

#define TSM(cond, slot) do { } while (0)
#define TSIF(cond, slot) do { if (__LINE__ >= FENCE_LO && __LINE__ < FENCE_HI) sched_fence(); } while (0)
__device__ __forceinline__ void sched_fence() {
  asm volatile("{\n.reg .pred p;\n.reg .u32 c;\nmov.u32 c, %%clock;\nsetp.eq.u32 p, c, 0;\n@p st.shared.u32 [%0], c;\n}"
               ::"r"(1024 + OFF_EPOCH + 4) : "memory");
}
#define TS(slot) TSIF(true, slot)

struct Params {
  const __nv_bfloat16 *q, *k, *v, *shift_k, *ssm_k, *ssm_D, *wqkv, *wo, *gate_w;
  __nv_bfloat16* out;
  uint32_t zero;
};

#define POLL_NS 0
constexpr int SPIN_LIMIT = 1 << 17;

__device__ __forceinline__ void mbar_init(uint32_t bar, uint32_t count) {
  asm volatile("mbarrier.init.shared::cta.b64 [%0], %1;" ::"r"(bar), "r"(count) : "memory");
}
__device__ __forceinline__ void mbar_expect_tx(uint32_t bar, uint32_t bytes) {
  asm volatile("mbarrier.arrive.expect_tx.shared::cta.b64 _, [%0], %1;" ::"r"(bar), "r"(bytes) : "memory");
}
__device__ __forceinline__ void mbar_arrive(uint32_t bar) {
  asm volatile("mbarrier.arrive.shared::cta.b64 _, [%0];" ::"r"(bar) : "memory");
}
__device__ __forceinline__ void mbar_wait(uint32_t bar, uint32_t parity) {
  uint32_t ok;
  int spins = 0;
  do {
    if (WAIT_NS)
      asm volatile("{\n.reg .pred p;\nmbarrier.try_wait.parity.shared::cta.b64 p, [%1], %2, %3;\nselp.b32 %0, 1, 0, p;\n}"
                   : "=r"(ok) : "r"(bar), "r"(parity), "r"(WAIT_NS) : "memory");
    else
      asm volatile("{\n.reg .pred p;\nmbarrier.try_wait.parity.shared::cta.b64 p, [%1], %2;\nselp.b32 %0, 1, 0, p;\n}"
                   : "=r"(ok) : "r"(bar), "r"(parity) : "memory");
    if (++spins > SPIN_LIMIT) break;
  } while (!ok);
}
__device__ __forceinline__ unsigned flag_read(const unsigned* p) {
  unsigned v;
  asm volatile("ld.relaxed.gpu.global.u32 %0, [%1];" : "=r"(v) : "l"(p) : "memory");
  return v;
}
__device__ __forceinline__ void flag_poll(const unsigned* p, unsigned target) {
  unsigned v;
  int spins = 0;
  do {
    if (POLL_NS && spins) __nanosleep(POLL_NS);
    asm volatile("ld.relaxed.gpu.global.u32 %0, [%1];" : "=r"(v) : "l"(p) : "memory");
    if (++spins > SPIN_LIMIT) break;
  } while ((int)(v - target) < 0);
}
__device__ __forceinline__ void flag_wait(const unsigned* p, unsigned target) {
  flag_poll(p, target);
  if (ACQ) asm volatile("fence.acquire.gpu;\nfence.proxy.async.global;" ::: "memory");
}
__device__ __forceinline__ void flag_signal(unsigned* p, int n, int lane) {
  if (lane == 0) asm volatile("fence.release.gpu;" ::: "memory");
  __syncwarp();
  if (lane < n) asm volatile("red.relaxed.gpu.global.add.u32 [%0], 1;" ::"l"(p + 32 * lane) : "memory");
}
__device__ __forceinline__ void flag_bump(unsigned* p) {
  asm volatile("red.relaxed.gpu.global.add.u32 [%0], 1;" ::"l"(p) : "memory");
}
__device__ __forceinline__ void fence_async_smem() { asm volatile("fence.proxy.async.shared::cta;" ::: "memory"); }
__device__ __forceinline__ void wg_sync(int id) { asm volatile("bar.sync %0, 128;" ::"r"(id) : "memory"); }

__device__ __forceinline__ void tma_2d(uint32_t dst, const CUtensorMap* tm, int c0, int c1, uint32_t bar) {
  asm volatile("cp.async.bulk.tensor.2d.shared::cluster.global.mbarrier::complete_tx::bytes [%0], [%1, {%3, %4}], [%2];"
               ::"r"(dst), "l"(tm), "r"(bar), "r"(c0), "r"(c1) : "memory");
}
__device__ __forceinline__ void tma_3d(uint32_t dst, const CUtensorMap* tm, int c0, int c1, int c2, uint32_t bar) {
  asm volatile("cp.async.bulk.tensor.3d.shared::cluster.global.mbarrier::complete_tx::bytes [%0], [%1, {%3, %4, %5}], [%2];"
               ::"r"(dst), "l"(tm), "r"(bar), "r"(c0), "r"(c1), "r"(c2) : "memory");
}
__device__ __forceinline__ void bulk_load(uint32_t dst, const void* src, uint32_t bytes, uint32_t bar) {
  asm volatile("cp.async.bulk.shared::cluster.global.mbarrier::complete_tx::bytes [%0], [%1], %2, [%3];"
               ::"r"(dst), "l"(src), "r"(bytes), "r"(bar) : "memory");
}
__device__ __forceinline__ void tm_prefetch(const CUtensorMap* tm) {
  asm volatile("prefetch.tensormap [%0];" ::"l"(tm) : "memory");
}

__device__ __forceinline__ void wg_fence() { asm volatile("wgmma.fence.sync.aligned;" ::: "memory"); }
__device__ __forceinline__ void wg_commit() { asm volatile("wgmma.commit_group.sync.aligned;" ::: "memory"); }
template <int N> __device__ __forceinline__ void wg_wait() { asm volatile("wgmma.wait_group.sync.aligned %0;" ::"n"(N) : "memory"); }
__device__ __forceinline__ uint32_t desc_lo(uint32_t addr, uint32_t lbo) { return ((addr & 0x3FFFF) >> 4) | ((lbo >> 4) << 16); }
constexpr uint32_t desc_hi(uint32_t sbo, uint32_t swz) { return (sbo >> 4) | (swz << 30); }
constexpr uint32_t HI_SW128 = desc_hi(1024, 1), HI_SW64 = desc_hi(512, 2), HI_SW32 = desc_hi(256, 3), HI_NONE = desc_hi(128, 0);
template <int N> __device__ __forceinline__ void pin(float* d) {
#pragma unroll
  for (int i = 0; i < N; i++) asm volatile("" : "+f"(d[i])::"memory");
}

__device__ __forceinline__ uint32_t lds32(uint32_t a) {
  uint32_t v;
  asm volatile("ld.volatile.shared.u32 %0, [%1];" : "=r"(v) : "r"(a) : "memory");
  return v;
}
__device__ __forceinline__ uint4 ldg128(const void* a) {
  uint4 v;
  asm volatile("ld.global.nc.v4.u32 {%0, %1, %2, %3}, [%4];" : "=r"(v.x), "=r"(v.y), "=r"(v.z), "=r"(v.w) : "l"(a) : "memory");
  return v;
}
__device__ __forceinline__ uint2 ldg64(const void* a) {
  uint2 v;
  asm volatile("ld.global.nc.v2.u32 {%0, %1}, [%2];" : "=r"(v.x), "=r"(v.y) : "l"(a) : "memory");
  return v;
}
__device__ __forceinline__ void ldsm4(uint32_t* r, uint32_t a) {
  asm volatile("ldmatrix.sync.aligned.m8n8.x4.shared.b16 {%0, %1, %2, %3}, [%4];"
               : "=r"(r[0]), "=r"(r[1]), "=r"(r[2]), "=r"(r[3]) : "r"(a) : "memory");
}
__device__ __forceinline__ void ldsm4t(uint32_t* r, uint32_t a) {
  asm volatile("ldmatrix.sync.aligned.m8n8.x4.trans.shared.b16 {%0, %1, %2, %3}, [%4];"
               : "=r"(r[0]), "=r"(r[1]), "=r"(r[2]), "=r"(r[3]) : "r"(a) : "memory");
}
__device__ __forceinline__ uint2 lds64(uint32_t a) {
  uint2 v;
  asm volatile("ld.shared.v2.u32 {%0, %1}, [%2];" : "=r"(v.x), "=r"(v.y) : "r"(a) : "memory");
  return v;
}
__device__ __forceinline__ uint4 lds128(uint32_t a) {
  uint4 v;
  asm volatile("ld.shared.v4.u32 {%0, %1, %2, %3}, [%4];" : "=r"(v.x), "=r"(v.y), "=r"(v.z), "=r"(v.w) : "r"(a) : "memory");
  return v;
}
__device__ __forceinline__ void sts128(uint32_t a, uint32_t x, uint32_t y, uint32_t z, uint32_t w) {
  asm volatile("st.shared.v4.u32 [%0], {%1, %2, %3, %4};" ::"r"(a), "r"(x), "r"(y), "r"(z), "r"(w) : "memory");
}
__device__ __forceinline__ void stsm4(uint32_t a, const uint32_t* r) {
  asm volatile("stmatrix.sync.aligned.m8n8.x4.shared.b16 [%0], {%1, %2, %3, %4};" ::"r"(a), "r"(r[0]), "r"(r[1]), "r"(r[2]), "r"(r[3]) : "memory");
}
__device__ __forceinline__ void stsm4t(uint32_t a, const uint32_t* r) {
  asm volatile("stmatrix.sync.aligned.m8n8.x4.trans.shared.b16 [%0], {%1, %2, %3, %4};" ::"r"(a), "r"(r[0]), "r"(r[1]), "r"(r[2]), "r"(r[3]) : "memory");
}
__device__ __forceinline__ uint32_t pack2(float lo, float hi) {
  uint32_t r;
  asm("cvt.rn.bf16x2.f32 %0, %1, %2;" : "=r"(r) : "f"(hi), "f"(lo));
  return r;
}
__device__ __forceinline__ uint32_t movm(uint32_t a) {
  uint32_t d;
  asm volatile("movmatrix.sync.aligned.m8n8.trans.b16 %0, %1;" : "=r"(d) : "r"(a));
  return d;
}
__device__ __forceinline__ uint32_t bmul(uint32_t a, uint32_t b) {
  uint32_t d;
  asm("mul.rn.bf16x2 %0, %1, %2;" : "=r"(d) : "r"(a), "r"(b));
  return d;
}
__device__ __forceinline__ uint32_t badd(uint32_t a, uint32_t b) {
  uint32_t d;
  asm("add.rn.bf16x2 %0, %1, %2;" : "=r"(d) : "r"(a), "r"(b));
  return d;
}
__device__ __forceinline__ uint32_t bfma(uint32_t a, uint32_t b, uint32_t c) {
  uint32_t d;
  asm("fma.rn.bf16x2 %0, %1, %2, %3;" : "=r"(d) : "r"(a), "r"(b), "r"(c));
  return d;
}
__device__ __forceinline__ float bf_lo(uint32_t x) { return __uint_as_float(x << 16); }
__device__ __forceinline__ float bf_hi(uint32_t x) { return __uint_as_float(x & 0xFFFF0000u); }
__device__ __forceinline__ float ex2(float x) {
  float y;
  asm("ex2.approx.ftz.f32 %0, %1;" : "=f"(y) : "f"(x));
  return y;
}
__device__ __forceinline__ float rcp(float x) {
  float y;
  asm("rcp.approx.ftz.f32 %0, %1;" : "=f"(y) : "f"(x));
  return y;
}
__device__ __forceinline__ void mma16816(float* d, uint32_t a0, uint32_t a1, uint32_t a2, uint32_t a3, uint32_t b0, uint32_t b1) {
  asm volatile("mma.sync.aligned.m16n8k16.row.col.f32.bf16.bf16.f32 {%0, %1, %2, %3}, {%4, %5, %6, %7}, {%8, %9}, {%0, %1, %2, %3};"
               : "+f"(d[0]), "+f"(d[1]), "+f"(d[2]), "+f"(d[3])
               : "r"(a0), "r"(a1), "r"(a2), "r"(a3), "r"(b0), "r"(b1));
}
__device__ __forceinline__ void mma1688(float* d, uint32_t a0, uint32_t a1, uint32_t b0) {
  asm volatile("mma.sync.aligned.m16n8k8.row.col.f32.bf16.bf16.f32 {%0, %1, %2, %3}, {%4, %5}, {%6}, {%0, %1, %2, %3};"
               : "+f"(d[0]), "+f"(d[1]), "+f"(d[2]), "+f"(d[3])
               : "r"(a0), "r"(a1), "r"(b0));
}

template <int N> struct WgRS;
template <int N> struct WgSST;
template <> struct WgRS<32> {
  template <uint32_t HB>
  static __device__ __forceinline__ void mma(float* d, const uint32_t* a, uint32_t db) {
    asm volatile("{\n.reg .pred p;\n.reg .b64 db;\nsetp.ne.b32 p, %22, 0;\n"
      "mov.b64 db, {%20, %21};\n"
      "wgmma.mma_async.sync.aligned.m64n32k16.f32.bf16.bf16 {"
      "%0, %1, %2, %3, %4, %5, %6, %7, %8, %9, %10, %11, %12, %13, %14, %15"
      "}, {%16, %17, %18, %19}, db, p, 1, 1, 1;\n}\n"
      : "+f"(d[0]), "+f"(d[1]), "+f"(d[2]), "+f"(d[3]), "+f"(d[4]), "+f"(d[5]), "+f"(d[6]), "+f"(d[7]),
        "+f"(d[8]), "+f"(d[9]), "+f"(d[10]), "+f"(d[11]), "+f"(d[12]), "+f"(d[13]), "+f"(d[14]), "+f"(d[15])
      : "r"(a[0]), "r"(a[1]), "r"(a[2]), "r"(a[3]), "r"(db), "n"(HB), "n"(1));
  }
  template <uint32_t HB>
  static __device__ __forceinline__ void set(float* d, const uint32_t* a, uint32_t db) {
    asm volatile("{\n.reg .pred p;\n.reg .b64 db;\nsetp.ne.b32 p, %22, 0;\n"
      "mov.b64 db, {%20, %21};\n"
      "wgmma.mma_async.sync.aligned.m64n32k16.f32.bf16.bf16 {"
      "%0, %1, %2, %3, %4, %5, %6, %7, %8, %9, %10, %11, %12, %13, %14, %15"
      "}, {%16, %17, %18, %19}, db, p, 1, 1, 1;\n}\n"
      : "=f"(d[0]), "=f"(d[1]), "=f"(d[2]), "=f"(d[3]), "=f"(d[4]), "=f"(d[5]), "=f"(d[6]), "=f"(d[7]),
        "=f"(d[8]), "=f"(d[9]), "=f"(d[10]), "=f"(d[11]), "=f"(d[12]), "=f"(d[13]), "=f"(d[14]), "=f"(d[15])
      : "r"(a[0]), "r"(a[1]), "r"(a[2]), "r"(a[3]), "r"(db), "n"(HB), "n"(0));
  }
};
template <> struct WgRS<64> {
  template <uint32_t HB>
  static __device__ __forceinline__ void mma(float* d, const uint32_t* a, uint32_t db) {
    asm volatile("{\n.reg .pred p;\n.reg .b64 db;\nsetp.ne.b32 p, %38, 0;\n"
      "mov.b64 db, {%36, %37};\n"
      "wgmma.mma_async.sync.aligned.m64n64k16.f32.bf16.bf16 {"
      "%0, %1, %2, %3, %4, %5, %6, %7, %8, %9, %10, %11, %12, %13, %14, %15, "
      "%16, %17, %18, %19, %20, %21, %22, %23, %24, %25, %26, %27, %28, %29, %30, %31"
      "}, {%32, %33, %34, %35}, db, p, 1, 1, 1;\n}\n"
      : "+f"(d[0]), "+f"(d[1]), "+f"(d[2]), "+f"(d[3]), "+f"(d[4]), "+f"(d[5]), "+f"(d[6]), "+f"(d[7]),
        "+f"(d[8]), "+f"(d[9]), "+f"(d[10]), "+f"(d[11]), "+f"(d[12]), "+f"(d[13]), "+f"(d[14]), "+f"(d[15]),
        "+f"(d[16]), "+f"(d[17]), "+f"(d[18]), "+f"(d[19]), "+f"(d[20]), "+f"(d[21]), "+f"(d[22]), "+f"(d[23]),
        "+f"(d[24]), "+f"(d[25]), "+f"(d[26]), "+f"(d[27]), "+f"(d[28]), "+f"(d[29]), "+f"(d[30]), "+f"(d[31])
      : "r"(a[0]), "r"(a[1]), "r"(a[2]), "r"(a[3]), "r"(db), "n"(HB), "n"(1));
  }
  template <uint32_t HB>
  static __device__ __forceinline__ void set(float* d, const uint32_t* a, uint32_t db) {
    asm volatile("{\n.reg .pred p;\n.reg .b64 db;\nsetp.ne.b32 p, %38, 0;\n"
      "mov.b64 db, {%36, %37};\n"
      "wgmma.mma_async.sync.aligned.m64n64k16.f32.bf16.bf16 {"
      "%0, %1, %2, %3, %4, %5, %6, %7, %8, %9, %10, %11, %12, %13, %14, %15, "
      "%16, %17, %18, %19, %20, %21, %22, %23, %24, %25, %26, %27, %28, %29, %30, %31"
      "}, {%32, %33, %34, %35}, db, p, 1, 1, 1;\n}\n"
      : "=f"(d[0]), "=f"(d[1]), "=f"(d[2]), "=f"(d[3]), "=f"(d[4]), "=f"(d[5]), "=f"(d[6]), "=f"(d[7]),
        "=f"(d[8]), "=f"(d[9]), "=f"(d[10]), "=f"(d[11]), "=f"(d[12]), "=f"(d[13]), "=f"(d[14]), "=f"(d[15]),
        "=f"(d[16]), "=f"(d[17]), "=f"(d[18]), "=f"(d[19]), "=f"(d[20]), "=f"(d[21]), "=f"(d[22]), "=f"(d[23]),
        "=f"(d[24]), "=f"(d[25]), "=f"(d[26]), "=f"(d[27]), "=f"(d[28]), "=f"(d[29]), "=f"(d[30]), "=f"(d[31])
      : "r"(a[0]), "r"(a[1]), "r"(a[2]), "r"(a[3]), "r"(db), "n"(HB), "n"(0));
  }
};
template <> struct WgSST<48> {
  template <uint32_t HA, uint32_t HB>
  static __device__ __forceinline__ void mma(float* d, uint32_t da, uint32_t db, int sc) {
    asm volatile("{\n.reg .pred p;\n.reg .b64 da, db;\nsetp.ne.b32 p, %28, 0;\n"
      "mov.b64 da, {%24, %25};\nmov.b64 db, {%26, %27};\n"
      "wgmma.mma_async.sync.aligned.m64n48k16.f32.bf16.bf16 {"
      "%0, %1, %2, %3, %4, %5, %6, %7, %8, %9, %10, %11, %12, %13, %14, %15, "
      "%16, %17, %18, %19, %20, %21, %22, %23"
      "}, da, db, p, 1, 1, 0, 1;\n}\n"
      : "+f"(d[0]), "+f"(d[1]), "+f"(d[2]), "+f"(d[3]), "+f"(d[4]), "+f"(d[5]), "+f"(d[6]), "+f"(d[7]),
        "+f"(d[8]), "+f"(d[9]), "+f"(d[10]), "+f"(d[11]), "+f"(d[12]), "+f"(d[13]), "+f"(d[14]), "+f"(d[15]),
        "+f"(d[16]), "+f"(d[17]), "+f"(d[18]), "+f"(d[19]), "+f"(d[20]), "+f"(d[21]), "+f"(d[22]), "+f"(d[23])
      : "r"(da), "n"(HA), "r"(db), "n"(HB), "r"(sc));
  }
};
template <> struct WgSST<80> {
  template <uint32_t HA, uint32_t HB>
  static __device__ __forceinline__ void mma(float* d, uint32_t da, uint32_t db, int sc) {
    asm volatile("{\n.reg .pred p;\n.reg .b64 da, db;\nsetp.ne.b32 p, %44, 0;\n"
      "mov.b64 da, {%40, %41};\nmov.b64 db, {%42, %43};\n"
      "wgmma.mma_async.sync.aligned.m64n80k16.f32.bf16.bf16 {"
      "%0, %1, %2, %3, %4, %5, %6, %7, %8, %9, %10, %11, %12, %13, %14, %15, "
      "%16, %17, %18, %19, %20, %21, %22, %23, %24, %25, %26, %27, %28, %29, %30, %31, "
      "%32, %33, %34, %35, %36, %37, %38, %39"
      "}, da, db, p, 1, 1, 0, 1;\n}\n"
      : "+f"(d[0]), "+f"(d[1]), "+f"(d[2]), "+f"(d[3]), "+f"(d[4]), "+f"(d[5]), "+f"(d[6]), "+f"(d[7]),
        "+f"(d[8]), "+f"(d[9]), "+f"(d[10]), "+f"(d[11]), "+f"(d[12]), "+f"(d[13]), "+f"(d[14]), "+f"(d[15]),
        "+f"(d[16]), "+f"(d[17]), "+f"(d[18]), "+f"(d[19]), "+f"(d[20]), "+f"(d[21]), "+f"(d[22]), "+f"(d[23]),
        "+f"(d[24]), "+f"(d[25]), "+f"(d[26]), "+f"(d[27]), "+f"(d[28]), "+f"(d[29]), "+f"(d[30]), "+f"(d[31]),
        "+f"(d[32]), "+f"(d[33]), "+f"(d[34]), "+f"(d[35]), "+f"(d[36]), "+f"(d[37]), "+f"(d[38]), "+f"(d[39])
      : "r"(da), "n"(HA), "r"(db), "n"(HB), "r"(sc));
  }
};
template <> struct WgSST<192> {
  template <uint32_t HA, uint32_t HB>
  static __device__ __forceinline__ void mma(float* d, uint32_t da, uint32_t db, int sc) {
    asm volatile("{\n.reg .pred p;\n.reg .b64 da, db;\nsetp.ne.b32 p, %100, 0;\n"
      "mov.b64 da, {%96, %97};\nmov.b64 db, {%98, %99};\n"
      "wgmma.mma_async.sync.aligned.m64n192k16.f32.bf16.bf16 {"
      "%0, %1, %2, %3, %4, %5, %6, %7, %8, %9, %10, %11, %12, %13, %14, %15, "
      "%16, %17, %18, %19, %20, %21, %22, %23, %24, %25, %26, %27, %28, %29, %30, %31, "
      "%32, %33, %34, %35, %36, %37, %38, %39, %40, %41, %42, %43, %44, %45, %46, %47, "
      "%48, %49, %50, %51, %52, %53, %54, %55, %56, %57, %58, %59, %60, %61, %62, %63, "
      "%64, %65, %66, %67, %68, %69, %70, %71, %72, %73, %74, %75, %76, %77, %78, %79, "
      "%80, %81, %82, %83, %84, %85, %86, %87, %88, %89, %90, %91, %92, %93, %94, %95"
      "}, da, db, p, 1, 1, 0, 1;\n}\n"
      : "+f"(d[0]), "+f"(d[1]), "+f"(d[2]), "+f"(d[3]), "+f"(d[4]), "+f"(d[5]), "+f"(d[6]), "+f"(d[7]),
        "+f"(d[8]), "+f"(d[9]), "+f"(d[10]), "+f"(d[11]), "+f"(d[12]), "+f"(d[13]), "+f"(d[14]), "+f"(d[15]),
        "+f"(d[16]), "+f"(d[17]), "+f"(d[18]), "+f"(d[19]), "+f"(d[20]), "+f"(d[21]), "+f"(d[22]), "+f"(d[23]),
        "+f"(d[24]), "+f"(d[25]), "+f"(d[26]), "+f"(d[27]), "+f"(d[28]), "+f"(d[29]), "+f"(d[30]), "+f"(d[31]),
        "+f"(d[32]), "+f"(d[33]), "+f"(d[34]), "+f"(d[35]), "+f"(d[36]), "+f"(d[37]), "+f"(d[38]), "+f"(d[39]),
        "+f"(d[40]), "+f"(d[41]), "+f"(d[42]), "+f"(d[43]), "+f"(d[44]), "+f"(d[45]), "+f"(d[46]), "+f"(d[47]),
        "+f"(d[48]), "+f"(d[49]), "+f"(d[50]), "+f"(d[51]), "+f"(d[52]), "+f"(d[53]), "+f"(d[54]), "+f"(d[55]),
        "+f"(d[56]), "+f"(d[57]), "+f"(d[58]), "+f"(d[59]), "+f"(d[60]), "+f"(d[61]), "+f"(d[62]), "+f"(d[63]),
        "+f"(d[64]), "+f"(d[65]), "+f"(d[66]), "+f"(d[67]), "+f"(d[68]), "+f"(d[69]), "+f"(d[70]), "+f"(d[71]),
        "+f"(d[72]), "+f"(d[73]), "+f"(d[74]), "+f"(d[75]), "+f"(d[76]), "+f"(d[77]), "+f"(d[78]), "+f"(d[79]),
        "+f"(d[80]), "+f"(d[81]), "+f"(d[82]), "+f"(d[83]), "+f"(d[84]), "+f"(d[85]), "+f"(d[86]), "+f"(d[87]),
        "+f"(d[88]), "+f"(d[89]), "+f"(d[90]), "+f"(d[91]), "+f"(d[92]), "+f"(d[93]), "+f"(d[94]), "+f"(d[95])
      : "r"(da), "n"(HA), "r"(db), "n"(HB), "r"(sc));
  }
};

struct FftConst {
  uint32_t f[2][4], fi[4][4];
  uint32_t ta[2][2], tb[2][2];
};
__device__ __forceinline__ void cis(int m, float scale, float& c, float& s) {
  const float a = (float)m * (-6.283185307179586f * scale);
  c = __cosf(a);
  s = __sinf(a);
}
__device__ __forceinline__ void fft_tables(uint32_t (&v)[12], int tw) {
  const int row = tw >> 2, ch = tw & 3;
#pragma unroll
  for (int i = 0; i < 4; i++) {
    float c[2], s[2], x[2];
#pragma unroll
    for (int e = 0; e < 2; e++) {
      cis((((32 * (8 * ch + 2 * i + e) + 15) * (4 * row - 63) + 2048) & 4095) - 2048, 1.f / 4096, c[e], s[e]);
      float gc, gs;
      cis((((row & 15) * (8 * (ch & 1) + 2 * i + e) + 8) & 15) - 8, 1.f / 16, gc, gs);
      x[e] = (row >> 4) == (ch >> 1) ? gc : (ch >> 1) ? gs : -gs;
    }
    v[i] = pack2(c[0] * 0.125f, c[1] * 0.125f);
    v[4 + i] = pack2(s[0] * 0.125f, s[1] * 0.125f);
    v[8 + i] = pack2(x[0], x[1]);
  }
#pragma unroll
  for (int i = 0; i < 12; i++) asm volatile("" : "+r"(v[i]));
}
__device__ __forceinline__ void fft_tables_store(const uint32_t (&v)[12], uint32_t sb, int tw) {
  const int row = tw >> 2;
  const uint32_t x = ((tw ^ (row >> 1)) & 3) << 4, a = sb + OFF_FT + (16 * (row >> 3) + (row & 7)) * 64 + x;
  sts128(a, v[0], v[1], v[2], v[3]);
  sts128(a + 512, v[4], v[5], v[6], v[7]);
  sts128(sb + OFF_GT + row * 64 + x, v[8], v[9], v[10], v[11]);
}
__device__ __forceinline__ void fft_twiddles(uint32_t (&v)[2], int tw) {
  float a[2], s[2];
#pragma unroll
  for (int i = 0; i < 2; i++) {
    float c;
    cis((2 * (2 * (tw & 3) + i) - 15) * (4 * (tw >> 2) - 63), 1.f / 4096, c, s[i]);
    a[i] = __fdividef(-s[i], 1.f + c);
  }
  v[0] = pack2(a[0], a[1]);
  v[1] = pack2(s[0], s[1]);
  asm volatile("" : "+r"(v[0]), "+r"(v[1]));
}
__device__ __forceinline__ void fft_matrices(FftConst& k, uint32_t sb, int w, int lane) {
  const uint32_t x = (lane >> 1) & 3;
  const uint2 t0 = lds64(sb + OFF_TT + 256 * w + 8 * lane), t1 = lds64(sb + OFF_TT + 256 * w + 8 * (lane ^ 3));
  k.ta[0][0] = t0.x;
  k.tb[0][0] = t0.y;
  k.ta[1][1] = __byte_perm(t1.x, 0, 0x1032);
  k.tb[1][1] = __byte_perm(t1.y, 0, 0x1032);
#pragma unroll
  for (int j = 0; j < 2; j++) {
    k.ta[1 - j][j] = k.ta[j][j] ^ 0x80008000u;
    k.tb[1 - j][j] = k.tb[j][j] ^ 0x80008000u;
    asm volatile("" : "+r"(k.ta[0][j]), "+r"(k.tb[0][j]), "+r"(k.ta[1][j]), "+r"(k.tb[1][j]));
  }
#pragma unroll
  for (int i = 0; i < 2; i++) {
    ldsm4(k.f[i], sb + OFF_FT + (16 * w + (lane & 15)) * 64 + (((2 * i + (lane >> 4)) ^ x) << 4));
    ldsm4t(k.fi[i], sb + OFF_FT + (32 * i + lane) * 64 + ((w ^ x) << 4));
#pragma unroll
    for (int j = 0; j < 4; j++) {
      k.fi[2 + i][j] = (j & 1) ? k.fi[i][j - 1] ^ 0x80008000u : k.fi[i][j + 1];
      asm volatile("" : "+r"(k.fi[2 + i][j]));
    }
  }
}
__device__ __forceinline__ void rot(uint32_t& x, uint32_t& y, uint32_t a, uint32_t b) {
  x = bfma(a, y, x);
  y = bfma(b, x, y);
  x = bfma(a, y, x);
}
__device__ __forceinline__ void twiddle_fwd(uint32_t (&a)[4][4], float* d, const FftConst& k) {
#pragma unroll
  for (int q = 0; q < 4; q++)
#pragma unroll
    for (int j = 0; j < 2; j++) {
      const float* x = d + 8 * q + 4 * j;
      uint32_t re = pack2(x[0], x[1]), im = pack2(x[2], x[3]);
      rot(re, im, k.ta[0][j], k.tb[0][j]);
      a[q & 2][2 * j + (q & 1)] = re;
      a[(q & 2) + 1][2 * j + (q & 1)] = im;
    }
}
__device__ __forceinline__ void g_step(float* d, const uint32_t (&a)[4][4], uint32_t dre, uint32_t dim) {
  WgRS<32>::set<HI_SW64>(d, a[0], dre);
  WgRS<32>::set<HI_SW64>(d + 16, a[2], dre);
  WgRS<32>::mma<HI_SW64>(d, a[1], dim);
  WgRS<32>::mma<HI_SW64>(d + 16, a[3], dim);
  wg_commit();
}

__device__ __forceinline__ void conv_channel(const FftConst& k, uint32_t sb, int c, int wg, int w, int lane) {
  const uint32_t cb = sb + off_ch(c), bars = sb + OFF_BAR;
  const uint32_t du = desc_lo(cb, 1024), dg = desc_lo(sb + OFF_GT, 16), dz = desc_lo(cb + U_BYTES, 16);
  float U[32], H[32];
  uint32_t a[4][4], e[4][4];
  const float dv = __uint_as_float(lds32(sb + OFF_D + 4 * c));
  wg_fence();
  WgRS<64>::set<HI_SW32>(H, k.f[0], du + 256);
  WgRS<64>::mma<HI_SW32>(H, k.f[1], du + 256 + 32);
  wg_commit();
  wg_wait<0>();
  pin<32>(H);
  twiddle_fwd(a, H, k);
  if (ATT_GATE) mbar_wait(bars + 8 * (ATT_GATE == 1 ? B_ATTN : B_ATT2), 0);
  mbar_wait(bars + 8 * (B_U + (c < 3 ? c : 3)), 0);
  TSM(w == 0 && c < 3, 7 + wg);
  wg_fence();
  WgRS<64>::set<HI_SW32>(U, k.f[0], du);
  WgRS<64>::mma<HI_SW32>(U, k.f[1], du + 32);
  wg_commit();
  g_step(H, a, dg, dg + 64);
  wg_wait<1>();
  pin<32>(U);
  twiddle_fwd(e, U, k);
  wg_fence();
  g_step(U, e, dg, dg + 64);
  wg_wait<0>();
  pin<32>(U);
  pin<32>(H);
#pragma unroll
  for (int j = 0; j < 2; j++) {
    float pr[4][2], pi[4][2];
#pragma unroll
    for (int x = 0; x < 2; x++) {
      H[4 * j + x] += dv;
#pragma unroll
      for (int m = 0; m < 4; m++) {
#pragma unroll
        for (int q = 0; q <= m; q++) {
          const int ih = 16 * (q >> 1) + 2 * (q & 1) + 4 * j + x, iu = 16 * ((m - q) >> 1) + 2 * ((m - q) & 1) + 4 * j + x;
          pr[m][x] = q ? fmaf(H[ih], U[iu], pr[m][x]) : H[ih] * U[iu];
          pi[m][x] = q ? fmaf(H[ih], U[iu + 8], pi[m][x]) : H[ih] * U[iu + 8];
          pr[m][x] = fmaf(-H[ih + 8], U[iu + 8], pr[m][x]);
          pi[m][x] = fmaf(H[ih + 8], U[iu], pi[m][x]);
        }
      }
    }
#pragma unroll
    for (int m = 0; m < 4; m++) {
      a[m & 2][2 * j + (m & 1)] = pack2(pr[m][0], pr[m][1]);
      a[(m & 2) + 1][2 * j + (m & 1)] = pack2(pi[m][0], pi[m][1]);
    }
  }
  wg_fence();
  g_step(U, a, dg + 64, dg);
  const uint32_t za = cb + U_BYTES + (8 * w + (lane & 7)) * 128 + (((lane >> 3) ^ (lane & 7)) << 4);
  const uint32_t ya = cb + (lane >> 4) * 1024 + (8 * w + (lane & 7)) * 32 + ((((lane >> 3) ^ (lane >> 2)) & 1) << 4);
  wg_sync(1 + wg);
  wg_wait<0>();
  pin<32>(U);
  TSIF(w == 0, 80 + c);
#pragma unroll
  for (int p = 0; p < 2; p++) {
#pragma unroll
    for (int i = 0; i < 4; i++) {
      const int j = i & 1;
      const float* x = U + 16 * p + 4 * j + (i & 2);
      e[p][i] = pack2(x[8], x[9]);
      e[2 + p][i] = pack2(x[0], x[1]);
      rot(e[p][i], e[2 + p][i], k.ta[1][j], k.tb[1][j]);
    }
    stsm4(za ^ (64 * p), e[p]);
    stsm4((za ^ (64 * p)) + 4096, e[2 + p]);
  }
  fence_async_smem();
  wg_sync(1 + wg);
  wg_fence();
  WgRS<64>::set<HI_SW128>(H, k.fi[0], dz);
#pragma unroll
  for (int ks = 1; ks < 4; ks++) WgRS<64>::mma<HI_SW128>(H, k.fi[ks], dz + 128 * ks);
  wg_commit();
  if (WO_FAST) mbar_wait(bars + 8 * B_ATTN, 0);
  wg_wait<0>();
  pin<32>(H);
  TSIF(w == 0, 88 + c);
#pragma unroll
  for (int j = 0; j < 8; j++)
    a[j >> 2][j & 3] = j < 2 ? pack2(H[4 * j], H[4 * j + 1]) : pack2(H[4 * j] + H[4 * j - 6], H[4 * j + 1] + H[4 * j - 5]);
  stsm4(ya, a[0]);
  stsm4(ya + 2048, a[1]);
  fence_async_smem();
  __syncwarp();
}

__device__ __forceinline__ void prep_slab(uint4* res, const uint2* sw, uint32_t sb, int slab, int w, int lane) {
  const int t = lane & 3, tp = (lane & 7) >> 1, pos = 8 * tp + 2 * (((lane >> 3) + tp) & 3) + (lane & 1);
  const uint32_t base = sb + OFF_KVS + slab * KVS_BYTES + pos * 128;
  uint32_t kk[2][4][4], vv[2][4];
  mbar_wait(sb + OFF_BAR + 8 * (B_KV + slab), 0);
#pragma unroll
  for (int h = 0; h < 2; h++) {
#pragma unroll
    for (int j = 0; j < 4; j++) {
      const uint32_t a = base + 128 * j;
      ldsm4t(kk[h][j], a + (((w + 4 * h) ^ ((a >> 7) & 7)) << 4));
    }
    const uint32_t a = base + KVS_V;
    ldsm4t(vv[h], a + (((w + 4 * h) ^ ((a >> 7) & 7)) << 4));
  }
#pragma unroll
  for (int h = 0; h < 2; h++) {
    uint32_t (&k)[4][4] = kk[h];
    uint32_t (&v)[4] = vv[h];
    const uint32_t w0 = __byte_perm(sw[h].x, 0, 0x1010), w1 = __byte_perm(sw[h].x, 0, 0x3232);
    const uint32_t w2 = __byte_perm(sw[h].y, 0, 0x1010), w3 = __byte_perm(sw[h].y, 0, 0x3232);
#pragma unroll
    for (int m = 0; m < 4; m++)
      v[m] = bmul(badd(badd(badd(bmul(k[0][m], w3), bmul(k[1][m], w2)), bmul(k[2][m], w1)), bmul(k[3][m], w0)), v[m]);
    uint32_t a[4];
#pragma unroll
    for (int m = 0; m < 4; m++) a[m] = (t & 1) ? v[(m + 3) & 3] : v[m];
    res[h] = (t & 2) ? make_uint4(a[2], a[3], a[0], a[1]) : make_uint4(a[0], a[1], a[2], a[3]);
  }
}

__device__ __forceinline__ void prep_gate(const Params& p, int b, int w, int lane) {
  uint2 gw[5], x[4][5];
#pragma unroll
  for (int j = 0; j < 5; j++) gw[j] = ldg64(reinterpret_cast<const uint2*>(p.gate_w) + lane + 32 * j);
#pragma unroll
  for (int i = 0; i < 4; i++)
#pragma unroll
    for (int j = 0; j < 5; j++)
      x[i][j] = ldg64(reinterpret_cast<const uint2*>(p.q) + (16 * b + 4 * w + i) * (DIM / 4) + lane + 32 * j);
  float s[4];
#pragma unroll
  for (int i = 0; i < 4; i++) {
    s[i] = 0.f;
#pragma unroll
    for (int j = 0; j < 5; j++) {
      const uint32_t m0 = bmul(x[i][j].x, gw[j].x), m1 = bmul(x[i][j].y, gw[j].y);
      s[i] += (bf_lo(m0) + bf_hi(m0)) + (bf_lo(m1) + bf_hi(m1));
    }
  }
  const bool h = lane & 16, q = lane & 8;
  const float a = (h ? s[2] : s[0]) + __shfl_xor_sync(0xffffffffu, h ? s[0] : s[2], 16);
  const float c = (h ? s[3] : s[1]) + __shfl_xor_sync(0xffffffffu, h ? s[1] : s[3], 16);
  float z = (q ? c : a) + __shfl_xor_sync(0xffffffffu, q ? a : c, 8);
#pragma unroll
  for (int o = 4; o > 0; o >>= 1) z += __shfl_xor_sync(0xffffffffu, z, o);
  z = bf_lo(pack2(z, 0.f));
  if ((lane & 7) == 0) g_gate[16 * b + 4 * w + (lane >> 3)] = bf_lo(pack2(__fdividef(1.f, 1.f + __expf(-z)), 0.f));
}

__device__ __forceinline__ uint32_t bmax(uint32_t a, uint32_t b) {
  uint32_t d;
  asm("max.bf16x2 %0, %1, %2;" : "=r"(d) : "r"(a), "r"(b));
  return d;
}
__device__ __forceinline__ void softmax_two(const float (&l)[2][2], uint32_t& p0, uint32_t& p1) {
  constexpr float kScale = 0.22360679774997896f, kLog2e = 1.4426950408889634f;
  const uint32_t r0 = pack2(l[0][0], l[1][0]), r1 = pack2(l[0][1], l[1][1]);
  const uint32_t x0 = pack2(bf_lo(r0) * kScale, bf_hi(r0) * kScale), x1 = pack2(bf_lo(r1) * kScale, bf_hi(r1) * kScale);
  uint32_t m = bmax(x0, x1);
  m = bmax(m, __shfl_xor_sync(0xffffffffu, m, 1));
  m = bmax(m, __shfl_xor_sync(0xffffffffu, m, 2));
  const float m0 = bf_lo(m) * kLog2e, m1 = bf_hi(m) * kLog2e;
  p0 = pack2(ex2(bf_lo(x0) * kLog2e - m0), ex2(bf_lo(x1) * kLog2e - m0));
  p1 = pack2(ex2(bf_hi(x0) * kLog2e - m1), ex2(bf_hi(x1) * kLog2e - m1));
}

__device__ __forceinline__ void halo_read(uint32_t (&kpv)[10], uint32_t (&vpv)[10], uint32_t (&tg)[7], const uint4* hp) {
#pragma unroll
  for (int j = 0; j < 7; j++) {
    uint32_t x0, x1, x2;
    asm volatile("ld.relaxed.gpu.global.v4.u32 {%0, %1, %2, %3}, [%4];"
                 : "=r"(x0), "=r"(x1), "=r"(x2), "=r"(tg[j]) : "l"(hp + 32 * j) : "memory");
    if (j < 4) kpv[3 * j] = x0; else vpv[3 * j - 10] = x0;
    if (j < 3) kpv[3 * j + 1] = x1; else vpv[3 * j - 9] = x1;
    if (j < 3) kpv[3 * j + 2] = x2; else if (j < 6) vpv[3 * j - 8] = x2;
  }
}

template <int ROT>
__device__ __forceinline__ void pack_qkv(const float* acc, uint32_t (&qlo)[10], uint32_t (&qhi)[10], uint32_t (&klo)[10],
                                         uint32_t (&khi)[10], uint32_t (&vlo)[10], uint32_t (&vhi)[10]) {
#pragma unroll
  for (int j = 0; j < 10; j++) {
    const int x = (j + ROT) % 10, tq = x < 8 ? x : 16 + x, tk = x < 8 ? 8 + x : 18 + x, tv = x < 8 ? 16 + x : 20 + x;
    khi[j] = pack2(acc[4 * tk + 2], acc[4 * tk + 3]);
    vhi[j] = movm(pack2(acc[4 * tv + 2], acc[4 * tv + 3]));
    qlo[j] = pack2(acc[4 * tq], acc[4 * tq + 1]);
    qhi[j] = pack2(acc[4 * tq + 2], acc[4 * tq + 3]);
    klo[j] = pack2(acc[4 * tk], acc[4 * tk + 1]);
    vlo[j] = pack2(acc[4 * tv], acc[4 * tv + 1]);
    asm volatile("" : "+r"(khi[j]), "+r"(qlo[j]), "+r"(qhi[j]), "+r"(klo[j]), "+r"(vlo[j]));
  }
}

template <int ROT> __device__ __forceinline__ void halo_send(const float* acc, uint4* ho, uint32_t tag) {
#pragma unroll
  for (int j = 0; j < 7; j++) {
    uint32_t x[3];
#pragma unroll
    for (int e = 0; e < 3; e++) {
      const int i = 3 * j + e, y = (i % 10 + ROT) % 10, tk = y < 8 ? 8 + y : 18 + y, tv = y < 8 ? 16 + y : 20 + y;
      x[e] = i < 10 ? pack2(acc[4 * tk + 2], acc[4 * tk + 3]) : i < 20 ? movm(pack2(acc[4 * tv + 2], acc[4 * tv + 3])) : 0u;
    }
    asm volatile("st.relaxed.gpu.global.v4.u32 [%0], {%1, %2, %3, %4};" ::"l"(ho + 32 * j), "r"(x[0]), "r"(x[1]), "r"(x[2]), "r"(tag) : "memory");
  }
}

__device__ __forceinline__ void attention(float* acc, uint32_t sb, int b, int par, int w, int lane, uint32_t tag, uint32_t zero) {
  const int g = lane >> 2, t = lane & 3;
  uint32_t klo[10], khi[10], vlo[10], vhi[10], qlo[10], qhi[10], kpv[10], vpv[10];
  if (HALO_FIRST && w == 3 && b < NCTA - 8) {
    uint4* ho = g_halo + (b * 2 + par) * 224 + lane;
    if (tail_first(b & 7)) halo_send<8>(acc, ho, tag);
    else halo_send<0>(acc, ho, tag);
    TSIF(par == 0, 76);
    pin<120>(acc);
  }
  if (tail_first(b & 7)) pack_qkv<8>(acc, qlo, qhi, klo, khi, vlo, vhi);
  else pack_qkv<0>(acc, qlo, qhi, klo, khi, vlo, vhi);
  const uint32_t xa = sb + OFF_KVX + (par * 3) * 2560 + lane * 16;
  if (w < 3) {
    sts128(xa + w * 2560, khi[0], khi[1], khi[2], khi[3]);
    sts128(xa + w * 2560 + 512, khi[4], khi[5], khi[6], khi[7]);
    sts128(xa + w * 2560 + 1024, khi[8], khi[9], vhi[0], vhi[1]);
    sts128(xa + w * 2560 + 1536, vhi[2], vhi[3], vhi[4], vhi[5]);
    sts128(xa + w * 2560 + 2048, vhi[6], vhi[7], vhi[8], vhi[9]);
  } else if (!HALO_FIRST && b < NCTA - 8) {
    uint4* ho = g_halo + (b * 2 + par) * 224 + lane;
#pragma unroll
    for (int j = 0; j < 7; j++) {
      const uint32_t x0 = j < 4 ? khi[3 * j] : vhi[3 * j - 10], x1 = j < 3 ? khi[3 * j + 1] : vhi[3 * j - 9];
      const uint32_t x2 = j < 3 ? khi[3 * j + 2] : j < 6 ? vhi[3 * j - 8] : 0u;
      asm volatile("st.relaxed.gpu.global.v4.u32 [%0], {%1, %2, %3, %4};" ::"l"(ho + 32 * j), "r"(x0), "r"(x1), "r"(x2), "r"(tag) : "memory");
    }
  }
  TSIF(par == 0 && w == 1, 64);
  TSIF(par == 0 && w == 3 && !HALO_FIRST, 76);
#pragma unroll
  for (int j = 0; j < 10; j++) vlo[j] = movm(vlo[j]);
  const bool far0 = 2 * t > g, far1 = 2 * t + 1 > g;
  const uint32_t mfar = (far0 ? 0x0000FFFFu : 0u) | (far1 ? 0xFFFF0000u : 0u);
  float slo[4][2], shi[4][2], lg[2][2];
  uint32_t phi[4], plo[4], qml[4], qmh[4];
#pragma unroll
  for (int h = 0; h < 4; h++) {
    const int f = h == 0 ? 0 : h == 1 ? 3 : h == 2 ? 5 : 8, hf = h < 2 ? 2 : 7;
    const bool mine = (h & 1) ? t >= 2 : t < 2;
    qml[h] = mine ? qlo[hf] : 0u;
    qmh[h] = mine ? qhi[hf] : 0u;
    float a[4] = {0.f, 0.f, 0.f, 0.f}, c[4] = {0.f, 0.f, 0.f, 0.f};
    mma16816(a, qlo[f], qhi[f], qlo[f + 1], qhi[f + 1], klo[f], klo[f + 1]);
    mma16816(c, qlo[f], qhi[f], qlo[f + 1], qhi[f + 1], khi[f], khi[f + 1]);
    mma1688(a, qml[h], qmh[h], klo[hf]);
    mma1688(c, qml[h], qmh[h], khi[hf]);
    slo[h][0] = a[0];
    slo[h][1] = a[1];
    shi[h][0] = lg[h & 1][0] = far0 ? a[2] : c[2];
    shi[h][1] = lg[h & 1][1] = far1 ? a[3] : c[3];
    if (!ATT_MERGE && (h & 1)) softmax_two(lg, phi[h - 1], phi[h]);
  }
  TSIF(par == 0 && w == 1, 65);
  if (ATT_GATE == 3 && lane == 0) mbar_arrive(sb + OFF_BAR + 8 * B_ATT2 + (phi[3] & zero));
  wg_sync(1 + par);
  TSIF(par == 0 && w == 1, 66);
  const bool nohist = (w == 0) && (b < 8);
  const uint4* hp = g_halo + ((b - 8) * 2 + par) * 224 + lane;
  uint32_t tg[7];
  if (w > 0) {
    const uint4 v0 = lds128(xa + (w - 1) * 2560), v1 = lds128(xa + (w - 1) * 2560 + 512), v2 = lds128(xa + (w - 1) * 2560 + 1024);
    const uint4 v3 = lds128(xa + (w - 1) * 2560 + 1536), v4 = lds128(xa + (w - 1) * 2560 + 2048);
    kpv[0] = v0.x; kpv[1] = v0.y; kpv[2] = v0.z; kpv[3] = v0.w; kpv[4] = v1.x; kpv[5] = v1.y; kpv[6] = v1.z; kpv[7] = v1.w;
    kpv[8] = v2.x; kpv[9] = v2.y; vpv[0] = v2.z; vpv[1] = v2.w; vpv[2] = v3.x; vpv[3] = v3.y; vpv[4] = v3.z; vpv[5] = v3.w;
    vpv[6] = v4.x; vpv[7] = v4.y; vpv[8] = v4.z; vpv[9] = v4.w;
  } else if (nohist) {
#pragma unroll
    for (int j = 0; j < 10; j++) kpv[j] = vpv[j] = 0u;
  } else {
    TSIF(par == 0, 77);
    halo_read(kpv, vpv, tg, hp);
  }
  if (w == 0 && !nohist) {
    int spins = 0;
    while (true) {
      bool ok = true;
#pragma unroll
      for (int j = 0; j < 7; j++) ok = ok && tg[j] == tag;
      if (__all_sync(0xffffffffu, ok) || ++spins > SPIN_LIMIT) break;
      halo_read(kpv, vpv, tg, hp);
    }
    TSIF(par == 0, 79);
  }
#pragma unroll
  for (int h = 0; h < 4; h++) {
    const int f = h == 0 ? 0 : h == 1 ? 3 : h == 2 ? 5 : 8, hf = h < 2 ? 2 : 7;
    float a[4] = {0.f, 0.f, 0.f, 0.f};
    mma16816(a, qlo[f], qhi[f], qlo[f + 1], qhi[f + 1], kpv[f], kpv[f + 1]);
    mma1688(a, qml[h], qmh[h], kpv[hf]);
    const float ninf = __int_as_float(0xff800000);
    lg[h & 1][0] = far0 ? (nohist ? ninf : a[0]) : slo[h][0];
    lg[h & 1][1] = far1 ? (nohist ? ninf : a[1]) : slo[h][1];
    if (h & 1) {
      softmax_two(lg, plo[h - 1], plo[h]);
      if (ATT_MERGE) {
        const float lh[2][2] = {{shi[h - 1][0], shi[h - 1][1]}, {shi[h][0], shi[h][1]}};
        softmax_two(lh, phi[h - 1], phi[h]);
      }
    }
  }
  TSIF(par == 0 && w <= 1, 67 + w);
  if (ATT_GATE == 2 && lane == 0) mbar_arrive(sb + OFF_BAR + 8 * B_ATT2 + (plo[3] & zero));
  uint32_t ov[20];
#pragma unroll
  for (int hp = 0; hp < 2; hp++) {
    const int hf = hp ? 7 : 2;
    float sh[4] = {0.f, 0.f, 0.f, 0.f}, i0 = 0.f, i1 = 0.f;
#pragma unroll
    for (int e = 0; e < 2; e++) {
      const int h = 2 * hp + e, f = h == 0 ? 0 : h == 1 ? 3 : h == 2 ? 5 : 8;
      const uint32_t a0 = plo[h] & mfar, a2 = plo[h] & ~mfar, a3 = phi[h] & mfar, c1 = phi[h] & ~mfar;
      float sum[4] = {0.f, 0.f, 0.f, 0.f};
      mma1688(sum, plo[h], phi[h], 0x3F803F80u);
      const float r0 = rcp(sum[0]), r1 = rcp(sum[2]);
#pragma unroll
      for (int j = f; j < f + 2; j++) {
        float o[4] = {0.f, 0.f, 0.f, 0.f};
        mma16816(o, a0, 0u, a2, a3, vpv[j], vlo[j]);
        mma1688(o, 0u, c1, vhi[j]);
        ov[2 * j] = pack2(o[0] * r0, o[1] * r0);
        ov[2 * j + 1] = pack2(o[2] * r1, o[3] * r1);
      }
      const bool mine = e ? g >= 4 : g < 4;
      mma16816(sh, a0, 0u, a2, a3, mine ? vpv[hf] : 0u, mine ? vlo[hf] : 0u);
      mma1688(sh, 0u, c1, mine ? vhi[hf] : 0u);
      if (e == 0 || t >= 2) {
        i0 = r0;
        i1 = r1;
      }
    }
    ov[2 * hf] = pack2(sh[0] * i0, sh[1] * i0);
    ov[2 * hf + 1] = pack2(sh[2] * i1, sh[3] * i1);
  }
  if (ATT_GATE == 4 && lane == 0) mbar_arrive(sb + OFF_BAR + 8 * B_ATT2 + (ov[19] & zero));
  TS(32 + 4 * par + w);
  mbar_wait(sb + OFF_BAR + 8 * B_P1, 0);
  const uint32_t oa = sb + OFF_OA + (lane >> 4) * 2048 + (32 * w + 2 * (lane & 15) + par) * 16;
#pragma unroll
  for (int j = 0; j < 5; j++) stsm4(oa + 4096 * j, ov + 4 * j);
  TSIF(par == 0 && w == 0, 120);
  fence_async_smem();
  TSIF(par == 0 && w == 0, 121);
  __syncwarp();
  if (lane == 0) mbar_arrive(sb + OFF_BAR + 8 * B_ATTN);
  TSM(w == 0 || w == 2, 122 + par + (w == 2 ? 3 : 0));
}

struct Maps {
  CUtensorMap x, wm, wt, k, v, y, wo, qm, qt, om, ot, u;
};

__device__ __forceinline__ void load_stage(uint32_t sb, int kb, int b, const Maps& m) {
  const uint32_t st = sb + (kb & 3) * STAGE_BYTES, bar = sb + OFF_BAR + 8 * (B_FULL1 + (kb & 3));
  const int r = b >> 3, hg = b & 7, slab = kb - KV_KB;
  const bool kv = slab >= 0 && slab < 5;
  const uint32_t kbar = sb + OFF_BAR + 8 * (B_KV + slab), dst = sb + OFF_KVS + slab * KVS_BYTES;
  mbar_expect_tx(bar, STAGE_BYTES);
  if (kv) mbar_expect_tx(kbar, KVS_BYTES);
  tma_3d(st, &m.x, 64 * kb, 64 * r, 0, bar);
  if (kv && KV_MIX) tma_3d(dst, &m.k, 0, 32 * (b >> 1) - 3, 2 * slab + (b & 1), kbar);
  tma_3d(st + ST_W, &m.wm, 80 * hg + (tail_first(hg) ? 16 : 0), 64 * kb, 0, bar);
  if (kv && KV_MIX) tma_3d(dst + KVS_V, &m.v, 0, 32 * (b >> 1), 2 * slab + (b & 1), kbar);
  tma_3d(st + ST_WT, &m.wt, 80 * hg + (tail_first(hg) ? 0 : 64), 64 * kb, 0, bar);
  if (kv && !KV_MIX) tma_3d(dst, &m.k, 0, 32 * (b >> 1) - 3, 2 * slab + (b & 1), kbar);
  if (kv && !KV_MIX) tma_3d(dst + KVS_V, &m.v, 0, 32 * (b >> 1), 2 * slab + (b & 1), kbar);
}

__global__ void __launch_bounds__(NTHR, 1) fused_kernel(const __grid_constant__ Maps m, const Params p) {
  extern __shared__ __align__(1024) uint8_t smem[];
  const uint32_t sb = (uint32_t)__cvta_generic_to_shared(smem);
  const uint32_t bars = sb + OFF_BAR;
  const int tid = threadIdx.x, lane = tid & 31;
  int b = blockIdx.x;
  if (BMAP == 1) b = (((b & 63) >> 3) * 2 + (b & 1)) * 8 + (((b < 64 ? 0x6521 : 0x7430) >> (4 * ((b >> 1) & 3))) & 7);
  if (BMAP == 2) b = ((b & 63) >> 2) * 8 + (((b < 64 ? 0x6521 : 0x7430) >> (4 * (b & 3))) & 7);
  if (BMAP == 3) b = (((b & 63) >> 3) * 2 + (b & 1)) * 8 + (((b < 64 ? 0x7430 : 0x6521) >> (4 * ((b >> 1) & 3))) & 7);
  if (BMAP == 4) b = (((b >> 4) * 2 + (b & 1)) * 8) + ((b >> 1) & 7);
  if (BMAP == 5) b = 127 - b;
  const int r = b >> 3, hg = b & 7;

  if (tid == T_ISSUE) {
    TSM(true, 0);
#pragma unroll
    for (int i = 0; i < 4; i++) mbar_init(bars + 8 * (B_FULL1 + i), 1);
#pragma unroll
    for (int i = 0; i < 3; i++) mbar_init(bars + 8 * (B_KV + i), 1);
    fence_async_smem();
#pragma unroll 1
    for (int kb = 0; kb <= PRE2; kb++) load_stage(sb, kb, b, m);
  } else if (tid >= T_PF && tid < T_PF + 12) {
    tm_prefetch(&m.x + (tid - T_PF));
  } else if (tid == T_INIT) {
#pragma unroll
    for (int i = 0; i < 4; i++) mbar_init(bars + 8 * (B_EMPTY1 + i), 8);
#pragma unroll
    for (int i = 0; i < 8; i++) mbar_init(bars + 8 * (B_FULL2 + i), 1);
#pragma unroll
    for (int i = 0; i < 4; i++) mbar_init(bars + 8 * (B_EMPTY2 + i), 8);
#pragma unroll
    for (int i = 0; i < 4; i++) mbar_init(bars + 8 * (B_U + i), 1);
    mbar_init(bars + 8 * B_HA, 4);
    mbar_init(bars + 8 * B_GATE, 4);
    mbar_init(bars + 8 * B_HB, 1);
    mbar_init(bars + 8 * B_KVD, 4);
    mbar_init(bars + 8 * B_QF, 1);
    mbar_init(bars + 8 * B_ATTN, 8);
    mbar_init(bars + 8 * B_ATT2, 8);
    mbar_init(bars + 8 * B_P1, 8);
    mbar_init(bars + 8 * B_C34, 1);
    mbar_init(bars + 8 * B_YRB, 1);
#pragma unroll
    for (int i = 0; i < 5; i++) mbar_init(bars + 8 * (B_YST + i), 4);
#pragma unroll
    for (int i = 0; i < 5; i++) mbar_init(bars + 8 * (B_US + i), U_TMA ? 4 : 1);
    mbar_init(bars + 8 * B_YSIG, 1);
    mbar_init(bars + 8 * B_YFULL, 1);
    mbar_init(bars + 8 * B_EPOCH, 1);
    mbar_init(bars + 8 * B_PREP, 4);
    mbar_init(bars + 8 * B_USIG, 1);
    mbar_init(bars + 8 * B_WST, 1);
#pragma unroll
    for (int i = 3; i < 5; i++) mbar_init(bars + 8 * (B_KV + i), 1);
    mbar_init(bars + 8 * B_E3, 8);
    mbar_init(bars + 8 * B_LAST, 1);
    mbar_init(bars + 8 * B_OSIG, 1);
    mbar_init(bars + 8 * B_WOP, 1);
    fence_async_smem();
  }
  const int warp = __shfl_sync(0xffffffffu, tid >> 5, 0), wg = warp >> 2, w = warp & 3;
  __syncthreads();

  if (wg == 3) {
    asm volatile("setmaxnreg.dec.sync.aligned.u32 56;");
    if (w == 0) {
      if (lane == 0) {
#pragma unroll 1
        for (int kb = 1 + PRE2; kb < 10; kb++) {
          if (kb >= 4) mbar_wait(bars + 8 * (kb == 7 ? B_E3 : B_EMPTY1 + (kb & 3)), (kb >> 3) & 1);
          TSIF(kb >= 4, 44 + kb);
          load_stage(sb, kb, b, m);
          TSIF(kb == 3, 60);
          if (kb == TRIG_KB) mbar_arrive(bars + 8 * B_LAST);
        }
        mbar_wait(bars + 8 * B_WOP, 0);
        mbar_wait(bars + 8 * WL_TRIG, 0);
        mbar_wait(bars + 8 * B_EPOCH, 0);
        flag_wait(g_cnt + C_W + 32 * hg, (lds32(sb + OFF_EPOCH) + 1) * 16);
        TS(30);
#pragma unroll 1
        for (int j = 0; j < 8; j++) {
          if (j >= 6) mbar_wait(bars + 8 * (B_EMPTY2 + j - 6), 0);
          if (j == 4) mbar_wait(bars + 8 * B_ATTN, 0);
          TSIF(j >= 6, 100 + j);
          if (RF_GATE && j == 6) mbar_wait(bars + 8 * B_YSIG, 0);
          mbar_expect_tx(bars + 8 * (B_FULL2 + j), j == 0 ? WO_BYTES : j == 5 ? O_BYTES + WO_BYTES + 512 : O_BYTES + WO_BYTES);
          bulk_load(sb + off_w(j), g_WO + (hg * 8 + step_src(hg, j)) * 800, WO_BYTES, bars + 8 * (B_FULL2 + j));
        }
        mbar_wait(bars + 8 * (B_EMPTY2 + Q_SLOT), 0);
        mbar_expect_tx(bars + 8 * B_QF, O_BYTES);
        tma_2d(sb + OFF_QS, &m.qm, 80 * hg, 128 * r, bars + 8 * B_QF);
        tma_2d(sb + OFF_QT, &m.qt, 80 * hg + 64, 128 * r, bars + 8 * B_QF);
      }
    } else if (w == 1) {
      unsigned epoch = 0;
      if (lane == 0) {
        epoch = atomicAdd(g_cnt + C_LAUNCH, 1u) / NCTA;
        asm volatile("st.shared.u32 [%0], %1;" ::"r"(sb + OFF_EPOCH), "r"(epoch) : "memory");
        mbar_arrive(bars + 8 * B_EPOCH);
        mbar_wait(bars + 8 * B_KVD, 0);
        mbar_expect_tx(bars + 8 * B_HB, 5 * 4096);
#pragma unroll 1
        for (int c = 0; c < 5; c++) {
          if (c == 3) mbar_wait(bars + 8 * B_S3, 0);
          bulk_load(sb + off_ch(c) + U_BYTES, p.ssm_k + (5 * b + c) * SEQ, 4096, bars + 8 * B_HB);
        }
#pragma unroll
        for (int c = 0; c < 4; c++) mbar_expect_tx(bars + 8 * (B_U + c), c < 3 ? U_BYTES : 2 * U_BYTES);
        const uint4* usrc = g_U + 5 * b * U_PITCH;
        mbar_wait(bars + 8 * B_USIG, 0);
        flag_wait(g_cnt + C_PREP + 32 * (b & 15), (epoch + 1) * NCTA);
        TS(23);
#pragma unroll
        for (int c = 0; c < 5; c++) {
          if (c == 3 && U_TRIM) mbar_wait(bars + 8 * (B_U + 2), 0);
          bulk_load(sb + off_ch(c), usrc + c * U_PITCH, U_BYTES, bars + 8 * (B_U + (c < 3 ? c : 3)));
          TSIF(c == 0 || c == 4, 116 + (c >> 2));
        }
      }
      epoch = __shfl_sync(0xffffffffu, epoch, 0);
      if (lane < 8) {
        const int src = (b & ~7) | step_src(hg, lane);
        mbar_wait(bars + 8 * OP_TRIG, 0);
        TS(20);
        bool seen = false;
#pragma unroll 1
        for (int spins = 0; spins < SPIN_LIMIT; spins++) {
          const bool now = !seen && (int)(flag_read(g_cnt + C_O + 32 * src) - (epoch + 1)) >= 0;
          if (now && lane >= 1 && lane < 4) bulk_load(sb + off_o(lane), g_O + src * 1280, O_BYTES, bars + 8 * (B_FULL2 + lane));
          seen = seen || now;
          if (__all_sync(0xff, seen)) break;
        }
        TS(21);
        if (lane == 5) bulk_load(sb + OFF_GATE, g_gate + 128 * r, 512, bars + 8 * (B_FULL2 + 5));
#pragma unroll 1
        for (int j = 4; j < 8; j++) {
          if (lane == j) {
            mbar_wait(bars + 8 * (j < 6 ? B_C34 : B_EMPTY2 + j - 6), 0);
            if (RF_GATE && j == 6) mbar_wait(bars + 8 * B_YSIG, 0);
            bulk_load(sb + off_o(j), g_O + src * 1280, O_BYTES, bars + 8 * (B_FULL2 + j));
          }
          __syncwarp(0xff);
        }
        TS(22);
      }
    } else if (w == 2) {
      mbar_wait(bars + 8 * B_PREP, 0);
      flag_signal(g_cnt + C_PREP, 16, lane);
      TS(25);
      if (lane == 0) mbar_arrive(bars + 8 * B_USIG);
      mbar_wait(bars + 8 * B_GATE, 0);
      if (((NOMB & 1) || O_RB) && lane == 0) asm volatile("fence.release.gpu;" ::: "memory");
      mbar_wait(bars + 8 * B_ATTN, 0);
      if (lane == 0) {
        if (O_DEFER) mbar_wait(bars + 8 * (B_U + 3), 0);
        asm volatile("cp.async.bulk.global.shared::cta.bulk_group [%0], [%1], 20480;\ncp.async.bulk.commit_group;"
                     ::"l"(g_O + b * 1280), "r"(sb + OFF_OA) : "memory");
        if (O_RB == 2) {
          asm volatile("cp.async.bulk.wait_group.read 0;" ::: "memory");
          mbar_expect_tx(bars + 8 * B_ORB, O_BYTES);
          bulk_load(sb + OFF_OA, g_O + b * 1280, O_BYTES, bars + 8 * B_ORB);
          mbar_wait(bars + 8 * B_ORB, 0);
          flag_bump(g_cnt + C_O + 32 * b);
        } else if (O_RB) asm volatile("cp.async.bulk.wait_group.read 0;" ::: "memory");
        else asm volatile("cp.async.bulk.wait_group 0;\nfence.proxy.async.global;" ::: "memory");
      }
      TS(74);
      if (O_RB == 2) {
      } else if (O_RB) {
        __syncwarp();
        unsigned v[5];
#pragma unroll
        for (int c = 0; c < 5; c++) v[c] = flag_read(reinterpret_cast<const unsigned*>(g_O + b * 1280 + 256 * c + 8 * lane + 7));
        const unsigned dep = __reduce_or_sync(0xffffffffu, (v[0] ^ v[1] ^ v[2] ^ v[3] ^ v[4]) & p.zero);
        if (lane == 0) flag_bump(g_cnt + C_O + 32 * b + dep);
      } else if (!(NOMB & 1)) flag_signal(g_cnt + C_O + 32 * b, 1, lane);
      else if (lane == 0) flag_bump(g_cnt + C_O + 32 * b);
      TS(26);
      if (lane == 0) mbar_arrive(bars + 8 * B_OSIG);

    } else {
      if (lane == 0) {
        uint4* dst = g_WO + (hg * 8 + (r >> 1)) * 800 + (r & 1) * 80;
        mbar_wait(bars + 8 * B_P1, 0);
        mbar_wait(bars + 8 * WB_TRIG, 0);
        mbar_expect_tx(bars + 8 * B_WST, WO_BYTES / 2);
        tma_3d(sb + OFF_WS, &m.wo, 0, 40 * r, 5 * hg, bars + 8 * B_WST);
        mbar_wait(bars + 8 * B_WST, 0);
        mbar_wait(bars + 8 * WO_TRIG, 0);
#pragma unroll 1
        for (int n = 0; n < 5; n++)
          asm volatile("cp.async.bulk.global.shared::cta.bulk_group [%0], [%1], 1280;" ::"l"(dst + 160 * n), "r"(sb + OFF_WS + 1280 * n) : "memory");
        asm volatile("cp.async.bulk.commit_group;\ncp.async.bulk.wait_group 0;\nfence.proxy.async.global;" ::: "memory");
        if (!(NOMB & 4)) asm volatile("fence.release.gpu;" ::: "memory");
        flag_bump(g_cnt + C_W + 32 * hg);
        mbar_arrive(bars + 8 * B_WOP);
        TS(71);
        mbar_expect_tx(bars + 8 * B_C34, 3 * U_BYTES);
        mbar_expect_tx(bars + 8 * B_YRB, 2 * U_BYTES);
#pragma unroll 1
        for (int c = 0; c < 5; c++) {
          mbar_wait(bars + 8 * (B_YST + c), 0);
          asm volatile("cp.async.bulk.global.shared::cta.bulk_group [%0], [%1], 4096;\ncp.async.bulk.commit_group;\n"
                       "cp.async.bulk.wait_group.read 0;" ::"l"(g_Y + (5 * b + c) * Y_PITCH), "r"(sb + off_ch(c)) : "memory");
          bulk_load(sb + off_ch(c), g_Y + (5 * b + c) * Y_PITCH, U_BYTES, bars + 8 * (c < 3 ? B_C34 : B_YRB));
        }
        TS(75);
        mbar_wait(bars + 8 * B_C34, 0);
        mbar_wait(bars + 8 * B_YRB, 0);
        flag_bump(g_cnt + C_Y + 32 * (b >> 4));
        TS(27);
        mbar_arrive(bars + 8 * B_YSIG);
        mbar_expect_tx(bars + 8 * B_YFULL, 20480);
        flag_wait(g_cnt + C_Y + 32 * hg, (lds32(sb + OFF_EPOCH) + 1) * 16);
        TS(24);
        tma_2d(sb + OFF_YT, &m.y, 128 * r, 80 * hg, bars + 8 * B_YFULL);
        tma_2d(sb + OFF_YT + 10240, &m.y, 128 * r + 64, 80 * hg, bars + 8 * B_YFULL);
      }
    }
  } else {
    asm volatile("setmaxnreg.inc.sync.aligned.u32 152;");
    if (wg < 2) {
      float acc[120];
#pragma unroll
      for (int i = 0; i < 120; i++) acc[i] = 0.f;
      const uint32_t da = desc_lo(sb + wg * 8192, 16), db = desc_lo(sb + ST_W, 8192), dc = desc_lo(sb + ST_WT, 2048);
      if (PW1) pin<120>(acc);
      if (PW1 == 2) mbar_wait(bars + 8 * B_FULL1, 0);
#pragma unroll 1
      for (int kb = 0; kb < 10; kb++) {
        mbar_wait(bars + 8 * (B_FULL1 + (kb & 3)), (kb >> 2) & 1);
        const uint32_t so = (kb & 3) * (STAGE_BYTES >> 4);
        wg_fence();
#pragma unroll
        for (int k = 0; k < 4; k++) {
          WgSST<192>::mma<HI_SW128, HI_SW128>(acc, da + so + 2 * k, db + so + 128 * k, 1);
          WgSST<48>::mma<HI_SW128, HI_SW32>(acc + 96, da + so + 2 * k, dc + so + 32 * k, 1);
        }
        wg_commit();
        wg_wait<1>();
        if (kb > 0 && lane == 0) mbar_arrive(bars + 8 * (kb == 4 ? B_E3 : B_EMPTY1 + ((kb - 1) & 3)));
      }
      mbar_wait(bars + 8 * B_EPOCH, 0);
      const uint32_t tag = lds32(sb + OFF_EPOCH) + 1;
      mbar_wait(bars + 8 * B_S3, 0);
      wg_wait<0>();
      pin<120>(acc);
      if (lane == 0) mbar_arrive(bars + 8 * B_P1);
      TSM(w == 0, 3 + wg);
      attention(acc, sb, b, wg, w, lane, tag, p.zero);
    } else {
      const int tw = tid & 127, chl = 64 * (b & 1) + 8 * w + (lane >> 2);
      uint4* up = g_U + chl * U_PITCH + ((4 * (b >> 1) + (lane & 3)) ^ ((b >> 2) & 1));
      uint2 sw[10];
      uint32_t dv = 0;
      if (lane < 5) dv = __ldg(reinterpret_cast<const unsigned short*>(p.ssm_D) + 5 * b + lane);
#pragma unroll
      for (int i = 0; i < 10; i++) sw[i] = ldg64(reinterpret_cast<const uint2*>(p.shift_k) + chl + 128 * (i >> 1) + 32 * (i & 1));
      uint32_t tab[12];
      uint32_t tt[2];
      fft_tables(tab, tw);
      fft_twiddles(tt, tw);
      uint4 res[10];
#pragma unroll
      for (int i = 0; i < 10; i++) res[i] = make_uint4(0, 0, 0, 0);
#pragma unroll 1
      for (int slab = 0; slab < 5; slab++) {
#pragma unroll
        for (int i = 0; i < 8; i++) res[i] = res[i + 2];
        prep_slab(res + 8, sw, sb, slab, w, lane);
        TSIF(w == 0, 99 + 4 * slab);
#pragma unroll
        for (int i = 0; i < 8; i++) sw[i] = sw[i + 2];
      }
      TSIF(w == 0, 28);
      __syncwarp();
      if (lane == 0) mbar_arrive(bars + 8 * B_KVD + ((res[8].x ^ res[9].x) & p.zero));
      mbar_wait(bars + 8 * B_KVD, 0);
      fft_tables_store(tab, sb, tw);
      mbar_wait(bars + 8 * B_LAST, 0);
#pragma unroll
      for (int i = 0; i < 10; i++) up[(128 * (i >> 1) + 32 * (i & 1)) * U_PITCH] = res[i];
      __syncwarp();
      if (lane == 0) mbar_arrive(bars + 8 * B_PREP);
      TSIF(w == 0 && !U_TMA, 5);
      mbar_wait(bars + 8 * (G_AFTER ? B_USIG : B_LAST), 0);
      prep_gate(p, b, w, lane);
      __syncwarp();
      if (lane == 0) mbar_arrive(bars + 8 * B_GATE);
      TSIF(w == 0, 72);
      mbar_wait(bars + 8 * B_HB, 0);
      TSIF(w == 0, 2);
      const uint32_t ha = sb + U_BYTES + ((tw >> 3) * 16 + 8 + (tw & 7)) * 16;
      uint4 hv[5];
#pragma unroll
      for (int c = 0; c < 5; c++) hv[c] = lds128(ha + off_ch(c));
      __syncwarp();
#pragma unroll
      for (int c = 0; c < 5; c++) sts128((ha ^ 16) + off_ch(c), hv[c].x, hv[c].y, hv[c].z, hv[c].w);
      asm volatile("st.shared.v2.u32 [%0], {%1, %2};" ::"r"(sb + OFF_TT + 8 * tw), "r"(tt[0]), "r"(tt[1]) : "memory");
      if (tw < 5) asm volatile("st.shared.f32 [%0], %1;" ::"r"(sb + OFF_D + 4 * tw), "f"(bf_lo(dv) * 0.125f) : "memory");
      fence_async_smem();
      __syncwarp();
      if (lane == 0) mbar_arrive(bars + 8 * B_HA);
      TSIF(w == 0, 6);
    }

    FftConst fc;
    TSM(w == 0 && wg == 0, 104);
    mbar_wait(bars + 8 * B_HA, 0);
    fft_matrices(fc, sb, w, lane);
    TSM(w == 0 && wg == 0, 105);
    TSM(w == 0 && wg == 2, 124);
#pragma unroll 1
    for (uint32_t tasks = wg == 0 ? TASK0 : wg == 1 ? TASK1 : TASK2; tasks; tasks >>= 4) {
      const int c = (tasks & 7) - 1;
      conv_channel(fc, sb, c, wg, w, lane);
      if (lane == 0) mbar_arrive(bars + 8 * (B_YST + c));
      TSM(w == 0, 10 + c);
    }

    if (wg < 2) {
      const int g = lane >> 2;
      float acc[40];
#pragma unroll
      for (int i = 0; i < 40; i++) acc[i] = 0.f;
      const uint32_t da = desc_lo(sb + wg * 1024, 2048), db = desc_lo(sb, 2560);
      if (!WO_FAST) mbar_wait(bars + 8 * (O_RB == 2 ? B_ORB : B_ATTN), 0);
      mbar_wait(bars + 8 * (B_YST + 3), 0);
      mbar_wait(bars + 8 * (B_YST + 4), 0);
      if (PW2 && !WO_FAST) mbar_wait(bars + 8 * B_FULL2, 0);
      TSM(w == 0, 15 + wg);
#pragma unroll 1
      for (int j = 0; j < 8; j++) {
        mbar_wait(bars + 8 * (B_FULL2 + j), 0);
        const uint32_t oa = da + (off_o(j) >> 4), ob = db + (off_w(j) >> 4);
        wg_fence();
#pragma unroll
        for (int k = 0; k < 5; k++) WgSST<80>::mma<HI_NONE, HI_SW32>(acc, oa + 256 * k, ob + 32 * k, 1);
        wg_commit();
        wg_wait<1>();
        if (j >= 1 && j <= Q_SLOT + 1 && lane == 0) mbar_arrive(bars + 8 * (B_EMPTY2 + j - 1));
      }
      TSIF(w == 0 && wg == 0, 113);
      const int tr = 64 * wg + 16 * w + (lane & 15);
      const uint32_t fm = sb + OFF_QS + tr * 128, fx = (lane >> 4) ^ (tr & 7);
      const uint32_t ft = sb + OFF_QT + tr * 32 + (((lane >> 4) ^ (tr >> 2)) & 1) * 16;
      const float g0 = __uint_as_float(lds32(sb + OFF_GATE + (64 * wg + 16 * w + g) * 4));
      const float g1 = __uint_as_float(lds32(sb + OFF_GATE + (64 * wg + 16 * w + 8 + g) * 4));
      const uint32_t ga = pack2(g0, g0), gb = pack2(g1, g1);
      const uint32_t na = pack2(1.f - g0, 1.f - g0), nb = pack2(1.f - g1, 1.f - g1);

      uint32_t qf[20];
      mbar_wait(bars + 8 * B_QF, 0);
#pragma unroll
      for (int j = 0; j < 5; j++) ldsm4(qf + 4 * j, j < 4 ? fm + ((fx ^ (2 * j)) << 4) : ft);
      if (FUSE_MIX) {
#pragma unroll
        for (int i = 0; i < 20; i++) {
          qf[i] = bmul((i & 1) ? gb : ga, qf[i]);
          asm volatile("" : "+r"(qf[i]));
        }
      }
      wg_wait<0>();
      pin<40>(acc);
      TSM(w == 0, 17 + wg);
      uint32_t pb[20];
#pragma unroll
      for (int j = 0; j < 10; j++) {
        pb[2 * j] = bmul(na, pack2(acc[4 * j], acc[4 * j + 1]));
        pb[2 * j + 1] = bmul(nb, pack2(acc[4 * j + 2], acc[4 * j + 3]));
        asm volatile("" : "+r"(pb[2 * j]), "+r"(pb[2 * j + 1]));
      }
      const uint32_t ya = sb + OFF_YT + wg * 10240 + ((lane >> 4) * 8 + (lane & 7)) * 128 +
                          (((2 * w + (((lane >> 3) & 1) ^ wg)) ^ (lane & 7)) << 4);
      mbar_wait(bars + 8 * B_YFULL, 0);
      TSM(w == 0 && wg == 0, 19);
#pragma unroll
      for (int j = 0; j < 5; j++) {
        uint32_t y[4];
        ldsm4t(y, ya + 2048 * j);
#pragma unroll
        for (int i = 0; i < 4; i++)
          qf[4 * j + i] = FUSE_MIX ? bfma(qf[4 * j + i], y[i], pb[4 * j + i]) : badd(bmul((i & 1) ? gb : ga, bmul(qf[4 * j + i], y[i])), pb[4 * j + i]);
      }
#pragma unroll
      for (int j = 0; j < 5; j++) stsm4(j < 4 ? fm + ((fx ^ (2 * j)) << 4) : ft, qf + 4 * j);
      fence_async_smem();
      __syncwarp();
      if (lane == 0) {
        const int row = 64 * wg + 16 * w;
        asm volatile("cp.async.bulk.tensor.2d.global.shared::cta.bulk_group [%0, {%2, %3}], [%1];"
                     ::"l"(&m.om), "r"(sb + OFF_QS + row * 128), "r"(80 * hg), "r"(128 * r + row) : "memory");
        asm volatile("cp.async.bulk.tensor.2d.global.shared::cta.bulk_group [%0, {%2, %3}], [%1];"
                     ::"l"(&m.ot), "r"(sb + OFF_QT + row * 32), "r"(80 * hg + 64), "r"(128 * r + row) : "memory");
        asm volatile("cp.async.bulk.commit_group;\ncp.async.bulk.wait_group.read 0;" ::: "memory");
      }
      TSM(true, 40 + 4 * wg + w);
      if (ENDBAR) asm volatile("bar.sync 15, 256;" ::: "memory");
    }
  }
}

typedef CUresult (*EncodeFn)(CUtensorMap*, CUtensorMapDataType, cuuint32_t, void*, const cuuint64_t*, const cuuint64_t*,
                             const cuuint32_t*, const cuuint32_t*, CUtensorMapInterleave, CUtensorMapSwizzle,
                             CUtensorMapL2promotion, CUtensorMapFloatOOBfill);

void encode(EncodeFn fn, CUtensorMap* tm, const void* base, int rank, const cuuint64_t* dims, const cuuint64_t* strides,
            const cuuint32_t* box, CUtensorMapSwizzle swz) {
  const cuuint32_t ones[3] = {1, 1, 1};
  fn(tm, CU_TENSOR_MAP_DATA_TYPE_BFLOAT16, rank, const_cast<void*>(base), dims, strides, box, ones,
     CU_TENSOR_MAP_INTERLEAVE_NONE, swz, CU_TENSOR_MAP_L2_PROMOTION_L2_128B, CU_TENSOR_MAP_FLOAT_OOB_FILL_NONE);
}

}

extern "C" void kernel_launch(void* const* d_in, const int* in_sizes, int n_in, void* d_out, int out_size) {
  (void)in_sizes; (void)n_in; (void)out_size;
  Params p;
  p.q = (const __nv_bfloat16*)d_in[0];
  p.k = (const __nv_bfloat16*)d_in[1];
  p.v = (const __nv_bfloat16*)d_in[2];
  p.shift_k = (const __nv_bfloat16*)d_in[3];
  p.ssm_k = (const __nv_bfloat16*)d_in[4];
  p.ssm_D = (const __nv_bfloat16*)d_in[5];
  p.wqkv = (const __nv_bfloat16*)d_in[7];
  p.wo = (const __nv_bfloat16*)d_in[8];
  p.gate_w = (const __nv_bfloat16*)d_in[9];
  p.out = (__nv_bfloat16*)d_out;
  p.zero = 0;

  static EncodeFn fn = nullptr;
  static void *yaddr = nullptr, *uaddr = nullptr;
  if (!fn) {
    cudaDriverEntryPointQueryResult qr;
    void* f = nullptr;
    cudaGetDriverEntryPoint("cuTensorMapEncodeTiled", &f, cudaEnableDefault, &qr);
    fn = (EncodeFn)f;
    cudaGetSymbolAddress(&yaddr, g_Y);
    cudaGetSymbolAddress(&uaddr, g_U);
    cudaFuncSetAttribute(fused_kernel, cudaFuncAttributeMaxDynamicSharedMemorySize, SMEM_BYTES);
  }
  Maps m;
  {
    const cuuint64_t dims[3] = {640, 1024, 2}, st[2] = {2560, 1280};
    const cuuint32_t box[3] = {64, 64, 2};
    encode(fn, &m.x, p.q, 3, dims, st, box, CU_TENSOR_MAP_SWIZZLE_128B);
  }
  {
    const cuuint64_t dims[3] = {640, 640, 3}, st[2] = {3840, 1280};
    const cuuint32_t box[3] = {64, 64, 3}, boxt[3] = {16, 64, 3};
    encode(fn, &m.wm, p.wqkv, 3, dims, st, box, CU_TENSOR_MAP_SWIZZLE_128B);
    encode(fn, &m.wt, p.wqkv, 3, dims, st, boxt, CU_TENSOR_MAP_SWIZZLE_32B);
  }
  {
    const cuuint64_t dims[3] = {64, 2048, 10}, st[2] = {1280, 128};
    const cuuint32_t boxk[3] = {64, 35, 1}, boxv[3] = {64, 32, 1};
    encode(fn, &m.k, p.k, 3, dims, st, boxk, CU_TENSOR_MAP_SWIZZLE_128B);
    encode(fn, &m.v, p.v, 3, dims, st, boxv, CU_TENSOR_MAP_SWIZZLE_128B);
  }
  {
    const cuuint64_t dims[3] = {16, 640, 40}, st[2] = {1280, 32};
    const cuuint32_t box[3] = {16, 40, 5};
    encode(fn, &m.wo, p.wo, 3, dims, st, box, CU_TENSOR_MAP_SWIZZLE_32B);
  }
  {
    const cuuint64_t dims[2] = {2048, 640}, st[1] = {Y_PITCH * 16};
    const cuuint32_t box[2] = {64, 80};
    encode(fn, &m.y, yaddr, 2, dims, st, box, CU_TENSOR_MAP_SWIZZLE_128B);
    const cuuint64_t stu[1] = {U_PITCH * 16};
    const cuuint32_t boxu[2] = {32, 64};
    encode(fn, &m.u, uaddr, 2, dims, stu, boxu, CU_TENSOR_MAP_SWIZZLE_NONE);
  }
  {
    const cuuint64_t dims[2] = {640, 2048}, st[1] = {1280};
    const cuuint32_t bqm[2] = {64, 128}, bqt[2] = {16, 128}, bom[2] = {64, 16}, bot[2] = {16, 16};
    encode(fn, &m.qm, p.q, 2, dims, st, bqm, CU_TENSOR_MAP_SWIZZLE_128B);
    encode(fn, &m.qt, p.q, 2, dims, st, bqt, CU_TENSOR_MAP_SWIZZLE_32B);
    encode(fn, &m.om, p.out, 2, dims, st, bom, CU_TENSOR_MAP_SWIZZLE_128B);
    encode(fn, &m.ot, p.out, 2, dims, st, bot, CU_TENSOR_MAP_SWIZZLE_32B);
  }
  fused_kernel<<<NCTA, NTHR, SMEM_BYTES>>>(m, p);
}
```

```cpp
#include <cuda.h>
#include <cuda_bf16.h>
#include <cuda_runtime.h>
#include <stdint.h>

namespace {

constexpr int SEQ = 2048, DIM = 640, NCTA = 128, NTHR = 512;

#define TRIG_KB 9
#define KV_KB 2
#define DEV_EXIT 0
#define ATT_GATE 0
#define G_AFTER 0
#define FENCE_LO 0
#define FENCE_HI 0
#define PW1 2
#define PW2 1
#define ENDBAR 0
#define PAD_KB 0
#define Y_ALIAS 1
#define NOMB 0
#define SRC_ROT 0
#define WAIT_NS 0
#define WB_TRIG B_USIG
#define G_POS 0
#define TAILF 1
#define T_ISSUE 384
#define T_PF 416
#define T_INIT 448
#define ATT_MERGE 0
#define BMAP 1
#define PRE2 1
#define KV_MIX 0
#define O_DEFER 0
#define TASK0 0x52
#define TASK1 0x3
#define TASK2 0x41
#define HALO_FIRST 1
#define PREV_EARLY 0
#define Y_RB 2
#define O_RB 2
#define O_EAGER 1
#define OP_TRIG B_ATTN
#define FUSE_MIX 1
#define Q_EARLY 1
#define WO_FAST 0
#define U_TRIM 1
#define Q_SLOT 3
#define G_TMA 1
#define W_RB 0
#define ACQ 0
#define U_TMA 0
#define U_GATE 0
#define RF_GATE 0
#define WO_TRIG B_WST
#define WL_TRIG B_WOP
#define WO_GATE 1

constexpr uint32_t STAGE_BYTES = 47104, ST_W = 16384, ST_WT = 40960;
constexpr uint32_t O_BYTES = 20480, WO_BYTES = 12800;
constexpr uint32_t OFF_OA = 0;
constexpr uint32_t OFF_QS = Q_SLOT * O_BYTES, OFF_QT = OFF_QS + 16384;
constexpr uint32_t OFF_WC = 81920;
constexpr uint32_t OFF_WA = 94720;
constexpr uint32_t OFF_GATE = 145920;
constexpr uint32_t OFF_TT = 146432;
constexpr uint32_t OFF_KVX = 148480;
constexpr uint32_t OFF_CH3 = 163840;
constexpr uint32_t CH_BYTES = 12288, U_BYTES = 4096;
constexpr uint32_t OFF_FT = 225280, OFF_GT = 229376;
constexpr uint32_t OFF_CH0 = 188416;
constexpr uint32_t OFF_KVS = OFF_CH0, KVS_V = 4480, KVS_BYTES = 8576;
constexpr uint32_t OFF_WS = OFF_WA;
__device__ __forceinline__ uint32_t off_us(int s) { return OFF_CH0 + 4096 * ((0x65320 >> (4 * s)) & 7); }
constexpr uint32_t OFF_YT = 163840;
constexpr uint32_t OFF_BAR = 231936;
constexpr uint32_t SMEM_BYTES = OFF_BAR + 512;

enum : uint32_t {
  B_FULL1 = 0, B_EMPTY1 = 4, B_S3 = 7, B_FULL2 = 52, B_EMPTY2 = 13, B_U = 8, B_GATE = 12, B_HA = 19, B_HB = 20,
  B_ATTN = 21, B_C34 = 22, B_YRB = 23, B_YFULL = 24, B_EPOCH = 25, B_PREP = 26, B_P1 = 27, B_LAST = 28,
  B_E3 = 29, B_OSIG = 30, B_WOP = 31, B_USIG = 32, B_WST = 33, B_KV = 34, B_KVD = 39, B_QF = 17, B_ATT2 = 18, B_YST = 40,
  B_ORB = 45, B_US = 45, B_YSIG = 50
};
constexpr uint32_t OFF_EPOCH = OFF_BAR + 8 * 51, OFF_D = OFF_BAR + 8 * 60;
__device__ __forceinline__ uint32_t off_o(int j) { return j < 4 ? OFF_OA + j * O_BYTES : j < 6 ? OFF_CH0 + (j - 4) * O_BYTES : OFF_OA + (j - 6) * O_BYTES; }
__device__ __forceinline__ uint32_t off_w(int j) { return j < 4 ? OFF_WA + j * WO_BYTES : j == 4 ? OFF_KVX : j == 5 ? OFF_WC : OFF_WA + (j - 6) * WO_BYTES; }
__device__ __forceinline__ int step_src(int hg, int j) {
  if (SRC_ROT == 2) {
    const int pos = (0x37621540 >> (4 * hg)) & 7;
    return j == 0 ? hg : (0x65217430 >> (4 * (j <= pos ? j - 1 : j))) & 7;
  }
  return SRC_ROT ? (hg + j) & 7 : j == 0 ? hg : j <= hg ? j - 1 : j;
}
__device__ __forceinline__ bool tail_first(int hg) { return TAILF && (hg & 3) == 3; }
__device__ __forceinline__ uint32_t off_ch(int c) { return (c < 3 ? OFF_CH0 : OFF_CH3 - 3 * CH_BYTES) + c * CH_BYTES; }

#define U_PITCH 264
__device__ __align__(1024) uint4 g_U[DIM * U_PITCH];
__device__ uint4 g_O[NCTA * 1280];
#define g_Y g_U
constexpr int Y_PITCH = U_PITCH;
__device__ uint4 g_WO[64 * 800];
__device__ uint4 g_halo[NCTA * 2 * 7 * 32];
__device__ __align__(128) float g_gate[SEQ + PAD_KB * 256];
__device__ unsigned g_cnt[32 * (1 + 2 * 16 + 8 + NCTA)];
constexpr int C_LAUNCH = 0, C_PREP = 32, C_Y = 32 * 17, C_W = 32 * 33, C_O = 32 * 41;

#define TSM(cond, slot) do { } while (0)
#define TSIF(cond, slot) do { if (__LINE__ >= FENCE_LO && __LINE__ < FENCE_HI) sched_fence(); } while (0)
__device__ __forceinline__ void sched_fence() {
  asm volatile("{\n.reg .pred p;\n.reg .u32 c;\nmov.u32 c, %%clock;\nsetp.eq.u32 p, c, 0;\n@p st.shared.u32 [%0], c;\n}"
               ::"r"(1024 + OFF_EPOCH + 4) : "memory");
}
#define TS(slot) TSIF(true, slot)

struct Params {
  const __nv_bfloat16 *q, *k, *v, *shift_k, *ssm_k, *ssm_D, *wqkv, *wo, *gate_w;
  __nv_bfloat16* out;
  uint32_t zero;
};

#define POLL_NS 0
constexpr int SPIN_LIMIT = 1 << 17;

__device__ __forceinline__ void mbar_init(uint32_t bar, uint32_t count) {
  asm volatile("mbarrier.init.shared::cta.b64 [%0], %1;" ::"r"(bar), "r"(count) : "memory");
}
__device__ __forceinline__ void mbar_expect_tx(uint32_t bar, uint32_t bytes) {
  asm volatile("mbarrier.arrive.expect_tx.shared::cta.b64 _, [%0], %1;" ::"r"(bar), "r"(bytes) : "memory");
}
__device__ __forceinline__ void mbar_arrive(uint32_t bar) {
  asm volatile("mbarrier.arrive.shared::cta.b64 _, [%0];" ::"r"(bar) : "memory");
}
__device__ __forceinline__ void mbar_wait(uint32_t bar, uint32_t parity) {
  uint32_t ok;
  int spins = 0;
  do {
    if (WAIT_NS)
      asm volatile("{\n.reg .pred p;\nmbarrier.try_wait.parity.shared::cta.b64 p, [%1], %2, %3;\nselp.b32 %0, 1, 0, p;\n}"
                   : "=r"(ok) : "r"(bar), "r"(parity), "r"(WAIT_NS) : "memory");
    else
      asm volatile("{\n.reg .pred p;\nmbarrier.try_wait.parity.shared::cta.b64 p, [%1], %2;\nselp.b32 %0, 1, 0, p;\n}"
                   : "=r"(ok) : "r"(bar), "r"(parity) : "memory");
    if (++spins > SPIN_LIMIT) break;
  } while (!ok);
}
__device__ __forceinline__ unsigned flag_read(const unsigned* p) {
  unsigned v;
  asm volatile("ld.relaxed.gpu.global.u32 %0, [%1];" : "=r"(v) : "l"(p) : "memory");
  return v;
}
__device__ __forceinline__ void flag_poll(const unsigned* p, unsigned target) {
  unsigned v;
  int spins = 0;
  do {
    if (POLL_NS && spins) __nanosleep(POLL_NS);
    asm volatile("ld.relaxed.gpu.global.u32 %0, [%1];" : "=r"(v) : "l"(p) : "memory");
    if (++spins > SPIN_LIMIT) break;
  } while ((int)(v - target) < 0);
}
__device__ __forceinline__ void flag_wait(const unsigned* p, unsigned target) {
  flag_poll(p, target);
  if (ACQ) asm volatile("fence.acquire.gpu;\nfence.proxy.async.global;" ::: "memory");
}
__device__ __forceinline__ void flag_signal(unsigned* p, int n, int lane) {
  if (lane == 0) asm volatile("fence.release.gpu;" ::: "memory");
  __syncwarp();
  if (lane < n) asm volatile("red.relaxed.gpu.global.add.u32 [%0], 1;" ::"l"(p + 32 * lane) : "memory");
}
__device__ __forceinline__ void flag_bump(unsigned* p) {
  asm volatile("red.relaxed.gpu.global.add.u32 [%0], 1;" ::"l"(p) : "memory");
}
__device__ __forceinline__ void fence_async_smem() { asm volatile("fence.proxy.async.shared::cta;" ::: "memory"); }
__device__ __forceinline__ void wg_sync(int id) { asm volatile("bar.sync %0, 128;" ::"r"(id) : "memory"); }

__device__ __forceinline__ void tma_2d(uint32_t dst, const CUtensorMap* tm, int c0, int c1, uint32_t bar) {
  asm volatile("cp.async.bulk.tensor.2d.shared::cluster.global.mbarrier::complete_tx::bytes [%0], [%1, {%3, %4}], [%2];"
               ::"r"(dst), "l"(tm), "r"(bar), "r"(c0), "r"(c1) : "memory");
}
__device__ __forceinline__ void tma_3d(uint32_t dst, const CUtensorMap* tm, int c0, int c1, int c2, uint32_t bar) {
  asm volatile("cp.async.bulk.tensor.3d.shared::cluster.global.mbarrier::complete_tx::bytes [%0], [%1, {%3, %4, %5}], [%2];"
               ::"r"(dst), "l"(tm), "r"(bar), "r"(c0), "r"(c1), "r"(c2) : "memory");
}
__device__ __forceinline__ void bulk_load(uint32_t dst, const void* src, uint32_t bytes, uint32_t bar) {
  asm volatile("cp.async.bulk.shared::cluster.global.mbarrier::complete_tx::bytes [%0], [%1], %2, [%3];"
               ::"r"(dst), "l"(src), "r"(bytes), "r"(bar) : "memory");
}
__device__ __forceinline__ void tm_prefetch(const CUtensorMap* tm) {
  asm volatile("prefetch.tensormap [%0];" ::"l"(tm) : "memory");
}

__device__ __forceinline__ void wg_fence() { asm volatile("wgmma.fence.sync.aligned;" ::: "memory"); }
__device__ __forceinline__ void wg_commit() { asm volatile("wgmma.commit_group.sync.aligned;" ::: "memory"); }
template <int N> __device__ __forceinline__ void wg_wait() { asm volatile("wgmma.wait_group.sync.aligned %0;" ::"n"(N) : "memory"); }
__device__ __forceinline__ uint32_t desc_lo(uint32_t addr, uint32_t lbo) { return ((addr & 0x3FFFF) >> 4) | ((lbo >> 4) << 16); }
constexpr uint32_t desc_hi(uint32_t sbo, uint32_t swz) { return (sbo >> 4) | (swz << 30); }
constexpr uint32_t HI_SW128 = desc_hi(1024, 1), HI_SW64 = desc_hi(512, 2), HI_SW32 = desc_hi(256, 3), HI_NONE = desc_hi(128, 0);
template <int N> __device__ __forceinline__ void pin(float* d) {
#pragma unroll
  for (int i = 0; i < N; i++) asm volatile("" : "+f"(d[i])::"memory");
}

__device__ __forceinline__ uint32_t lds32(uint32_t a) {
  uint32_t v;
  asm volatile("ld.volatile.shared.u32 %0, [%1];" : "=r"(v) : "r"(a) : "memory");
  return v;
}
__device__ __forceinline__ uint4 ldg128(const void* a) {
  uint4 v;
  asm volatile("ld.global.nc.v4.u32 {%0, %1, %2, %3}, [%4];" : "=r"(v.x), "=r"(v.y), "=r"(v.z), "=r"(v.w) : "l"(a) : "memory");
  return v;
}
__device__ __forceinline__ uint2 ldg64(const void* a) {
  uint2 v;
  asm volatile("ld.global.nc.v2.u32 {%0, %1}, [%2];" : "=r"(v.x), "=r"(v.y) : "l"(a) : "memory");
  return v;
}
__device__ __forceinline__ void ldsm4(uint32_t* r, uint32_t a) {
  asm volatile("ldmatrix.sync.aligned.m8n8.x4.shared.b16 {%0, %1, %2, %3}, [%4];"
               : "=r"(r[0]), "=r"(r[1]), "=r"(r[2]), "=r"(r[3]) : "r"(a) : "memory");
}
__device__ __forceinline__ void ldsm4t(uint32_t* r, uint32_t a) {
  asm volatile("ldmatrix.sync.aligned.m8n8.x4.trans.shared.b16 {%0, %1, %2, %3}, [%4];"
               : "=r"(r[0]), "=r"(r[1]), "=r"(r[2]), "=r"(r[3]) : "r"(a) : "memory");
}
__device__ __forceinline__ uint2 lds64(uint32_t a) {
  uint2 v;
  asm volatile("ld.shared.v2.u32 {%0, %1}, [%2];" : "=r"(v.x), "=r"(v.y) : "r"(a) : "memory");
  return v;
}
__device__ __forceinline__ uint4 lds128(uint32_t a) {
  uint4 v;
  asm volatile("ld.shared.v4.u32 {%0, %1, %2, %3}, [%4];" : "=r"(v.x), "=r"(v.y), "=r"(v.z), "=r"(v.w) : "r"(a) : "memory");
  return v;
}
__device__ __forceinline__ void sts128(uint32_t a, uint32_t x, uint32_t y, uint32_t z, uint32_t w) {
  asm volatile("st.shared.v4.u32 [%0], {%1, %2, %3, %4};" ::"r"(a), "r"(x), "r"(y), "r"(z), "r"(w) : "memory");
}
__device__ __forceinline__ void stsm4(uint32_t a, const uint32_t* r) {
  asm volatile("stmatrix.sync.aligned.m8n8.x4.shared.b16 [%0], {%1, %2, %3, %4};" ::"r"(a), "r"(r[0]), "r"(r[1]), "r"(r[2]), "r"(r[3]) : "memory");
}
__device__ __forceinline__ void stsm4t(uint32_t a, const uint32_t* r) {
  asm volatile("stmatrix.sync.aligned.m8n8.x4.trans.shared.b16 [%0], {%1, %2, %3, %4};" ::"r"(a), "r"(r[0]), "r"(r[1]), "r"(r[2]), "r"(r[3]) : "memory");
}
__device__ __forceinline__ uint32_t pack2(float lo, float hi) {
  uint32_t r;
  asm("cvt.rn.bf16x2.f32 %0, %1, %2;" : "=r"(r) : "f"(hi), "f"(lo));
  return r;
}
__device__ __forceinline__ uint32_t movm(uint32_t a) {
  uint32_t d;
  asm volatile("movmatrix.sync.aligned.m8n8.trans.b16 %0, %1;" : "=r"(d) : "r"(a));
  return d;
}
__device__ __forceinline__ uint32_t bmul(uint32_t a, uint32_t b) {
  uint32_t d;
  asm("mul.rn.bf16x2 %0, %1, %2;" : "=r"(d) : "r"(a), "r"(b));
  return d;
}
__device__ __forceinline__ uint32_t badd(uint32_t a, uint32_t b) {
  uint32_t d;
  asm("add.rn.bf16x2 %0, %1, %2;" : "=r"(d) : "r"(a), "r"(b));
  return d;
}
__device__ __forceinline__ uint32_t bfma(uint32_t a, uint32_t b, uint32_t c) {
  uint32_t d;
  asm("fma.rn.bf16x2 %0, %1, %2, %3;" : "=r"(d) : "r"(a), "r"(b), "r"(c));
  return d;
}
__device__ __forceinline__ float bf_lo(uint32_t x) { return __uint_as_float(x << 16); }
__device__ __forceinline__ float bf_hi(uint32_t x) { return __uint_as_float(x & 0xFFFF0000u); }
__device__ __forceinline__ float ex2(float x) {
  float y;
  asm("ex2.approx.ftz.f32 %0, %1;" : "=f"(y) : "f"(x));
  return y;
}
__device__ __forceinline__ float rcp(float x) {
  float y;
  asm("rcp.approx.ftz.f32 %0, %1;" : "=f"(y) : "f"(x));
  return y;
}
__device__ __forceinline__ void mma16816(float* d, uint32_t a0, uint32_t a1, uint32_t a2, uint32_t a3, uint32_t b0, uint32_t b1) {
  asm volatile("mma.sync.aligned.m16n8k16.row.col.f32.bf16.bf16.f32 {%0, %1, %2, %3}, {%4, %5, %6, %7}, {%8, %9}, {%0, %1, %2, %3};"
               : "+f"(d[0]), "+f"(d[1]), "+f"(d[2]), "+f"(d[3])
               : "r"(a0), "r"(a1), "r"(a2), "r"(a3), "r"(b0), "r"(b1));
}
__device__ __forceinline__ void mma1688(float* d, uint32_t a0, uint32_t a1, uint32_t b0) {
  asm volatile("mma.sync.aligned.m16n8k8.row.col.f32.bf16.bf16.f32 {%0, %1, %2, %3}, {%4, %5}, {%6}, {%0, %1, %2, %3};"
               : "+f"(d[0]), "+f"(d[1]), "+f"(d[2]), "+f"(d[3])
               : "r"(a0), "r"(a1), "r"(b0));
}

template <int N> struct WgRS;
template <int N> struct WgSST;
template <> struct WgRS<32> {
  template <uint32_t HB>
  static __device__ __forceinline__ void mma(float* d, const uint32_t* a, uint32_t db) {
    asm volatile("{\n.reg .pred p;\n.reg .b64 db;\nsetp.ne.b32 p, %22, 0;\n"
      "mov.b64 db, {%20, %21};\n"
      "wgmma.mma_async.sync.aligned.m64n32k16.f32.bf16.bf16 {"
      "%0, %1, %2, %3, %4, %5, %6, %7, %8, %9, %10, %11, %12, %13, %14, %15"
      "}, {%16, %17, %18, %19}, db, p, 1, 1, 1;\n}\n"
      : "+f"(d[0]), "+f"(d[1]), "+f"(d[2]), "+f"(d[3]), "+f"(d[4]), "+f"(d[5]), "+f"(d[6]), "+f"(d[7]),
        "+f"(d[8]), "+f"(d[9]), "+f"(d[10]), "+f"(d[11]), "+f"(d[12]), "+f"(d[13]), "+f"(d[14]), "+f"(d[15])
      : "r"(a[0]), "r"(a[1]), "r"(a[2]), "r"(a[3]), "r"(db), "n"(HB), "n"(1));
  }
  template <uint32_t HB>
  static __device__ __forceinline__ void set(float* d, const uint32_t* a, uint32_t db) {
    asm volatile("{\n.reg .pred p;\n.reg .b64 db;\nsetp.ne.b32 p, %22, 0;\n"
      "mov.b64 db, {%20, %21};\n"
      "wgmma.mma_async.sync.aligned.m64n32k16.f32.bf16.bf16 {"
      "%0, %1, %2, %3, %4, %5, %6, %7, %8, %9, %10, %11, %12, %13, %14, %15"
      "}, {%16, %17, %18, %19}, db, p, 1, 1, 1;\n}\n"
      : "=f"(d[0]), "=f"(d[1]), "=f"(d[2]), "=f"(d[3]), "=f"(d[4]), "=f"(d[5]), "=f"(d[6]), "=f"(d[7]),
        "=f"(d[8]), "=f"(d[9]), "=f"(d[10]), "=f"(d[11]), "=f"(d[12]), "=f"(d[13]), "=f"(d[14]), "=f"(d[15])
      : "r"(a[0]), "r"(a[1]), "r"(a[2]), "r"(a[3]), "r"(db), "n"(HB), "n"(0));
  }
};
template <> struct WgRS<64> {
  template <uint32_t HB>
  static __device__ __forceinline__ void mma(float* d, const uint32_t* a, uint32_t db) {
    asm volatile("{\n.reg .pred p;\n.reg .b64 db;\nsetp.ne.b32 p, %38, 0;\n"
      "mov.b64 db, {%36, %37};\n"
      "wgmma.mma_async.sync.aligned.m64n64k16.f32.bf16.bf16 {"
      "%0, %1, %2, %3, %4, %5, %6, %7, %8, %9, %10, %11, %12, %13, %14, %15, "
      "%16, %17, %18, %19, %20, %21, %22, %23, %24, %25, %26, %27, %28, %29, %30, %31"
      "}, {%32, %33, %34, %35}, db, p, 1, 1, 1;\n}\n"
      : "+f"(d[0]), "+f"(d[1]), "+f"(d[2]), "+f"(d[3]), "+f"(d[4]), "+f"(d[5]), "+f"(d[6]), "+f"(d[7]),
        "+f"(d[8]), "+f"(d[9]), "+f"(d[10]), "+f"(d[11]), "+f"(d[12]), "+f"(d[13]), "+f"(d[14]), "+f"(d[15]),
        "+f"(d[16]), "+f"(d[17]), "+f"(d[18]), "+f"(d[19]), "+f"(d[20]), "+f"(d[21]), "+f"(d[22]), "+f"(d[23]),
        "+f"(d[24]), "+f"(d[25]), "+f"(d[26]), "+f"(d[27]), "+f"(d[28]), "+f"(d[29]), "+f"(d[30]), "+f"(d[31])
      : "r"(a[0]), "r"(a[1]), "r"(a[2]), "r"(a[3]), "r"(db), "n"(HB), "n"(1));
  }
  template <uint32_t HB>
  static __device__ __forceinline__ void set(float* d, const uint32_t* a, uint32_t db) {
    asm volatile("{\n.reg .pred p;\n.reg .b64 db;\nsetp.ne.b32 p, %38, 0;\n"
      "mov.b64 db, {%36, %37};\n"
      "wgmma.mma_async.sync.aligned.m64n64k16.f32.bf16.bf16 {"
      "%0, %1, %2, %3, %4, %5, %6, %7, %8, %9, %10, %11, %12, %13, %14, %15, "
      "%16, %17, %18, %19, %20, %21, %22, %23, %24, %25, %26, %27, %28, %29, %30, %31"
      "}, {%32, %33, %34, %35}, db, p, 1, 1, 1;\n}\n"
      : "=f"(d[0]), "=f"(d[1]), "=f"(d[2]), "=f"(d[3]), "=f"(d[4]), "=f"(d[5]), "=f"(d[6]), "=f"(d[7]),
        "=f"(d[8]), "=f"(d[9]), "=f"(d[10]), "=f"(d[11]), "=f"(d[12]), "=f"(d[13]), "=f"(d[14]), "=f"(d[15]),
        "=f"(d[16]), "=f"(d[17]), "=f"(d[18]), "=f"(d[19]), "=f"(d[20]), "=f"(d[21]), "=f"(d[22]), "=f"(d[23]),
        "=f"(d[24]), "=f"(d[25]), "=f"(d[26]), "=f"(d[27]), "=f"(d[28]), "=f"(d[29]), "=f"(d[30]), "=f"(d[31])
      : "r"(a[0]), "r"(a[1]), "r"(a[2]), "r"(a[3]), "r"(db), "n"(HB), "n"(0));
  }
};
template <> struct WgSST<48> {
  template <uint32_t HA, uint32_t HB>
  static __device__ __forceinline__ void mma(float* d, uint32_t da, uint32_t db, int sc) {
    asm volatile("{\n.reg .pred p;\n.reg .b64 da, db;\nsetp.ne.b32 p, %28, 0;\n"
      "mov.b64 da, {%24, %25};\nmov.b64 db, {%26, %27};\n"
      "wgmma.mma_async.sync.aligned.m64n48k16.f32.bf16.bf16 {"
      "%0, %1, %2, %3, %4, %5, %6, %7, %8, %9, %10, %11, %12, %13, %14, %15, "
      "%16, %17, %18, %19, %20, %21, %22, %23"
      "}, da, db, p, 1, 1, 0, 1;\n}\n"
      : "+f"(d[0]), "+f"(d[1]), "+f"(d[2]), "+f"(d[3]), "+f"(d[4]), "+f"(d[5]), "+f"(d[6]), "+f"(d[7]),
        "+f"(d[8]), "+f"(d[9]), "+f"(d[10]), "+f"(d[11]), "+f"(d[12]), "+f"(d[13]), "+f"(d[14]), "+f"(d[15]),
        "+f"(d[16]), "+f"(d[17]), "+f"(d[18]), "+f"(d[19]), "+f"(d[20]), "+f"(d[21]), "+f"(d[22]), "+f"(d[23])
      : "r"(da), "n"(HA), "r"(db), "n"(HB), "r"(sc));
  }
};
template <> struct WgSST<80> {
  template <uint32_t HA, uint32_t HB>
  static __device__ __forceinline__ void mma(float* d, uint32_t da, uint32_t db, int sc) {
    asm volatile("{\n.reg .pred p;\n.reg .b64 da, db;\nsetp.ne.b32 p, %44, 0;\n"
      "mov.b64 da, {%40, %41};\nmov.b64 db, {%42, %43};\n"
      "wgmma.mma_async.sync.aligned.m64n80k16.f32.bf16.bf16 {"
      "%0, %1, %2, %3, %4, %5, %6, %7, %8, %9, %10, %11, %12, %13, %14, %15, "
      "%16, %17, %18, %19, %20, %21, %22, %23, %24, %25, %26, %27, %28, %29, %30, %31, "
      "%32, %33, %34, %35, %36, %37, %38, %39"
      "}, da, db, p, 1, 1, 0, 1;\n}\n"
      : "+f"(d[0]), "+f"(d[1]), "+f"(d[2]), "+f"(d[3]), "+f"(d[4]), "+f"(d[5]), "+f"(d[6]), "+f"(d[7]),
        "+f"(d[8]), "+f"(d[9]), "+f"(d[10]), "+f"(d[11]), "+f"(d[12]), "+f"(d[13]), "+f"(d[14]), "+f"(d[15]),
        "+f"(d[16]), "+f"(d[17]), "+f"(d[18]), "+f"(d[19]), "+f"(d[20]), "+f"(d[21]), "+f"(d[22]), "+f"(d[23]),
        "+f"(d[24]), "+f"(d[25]), "+f"(d[26]), "+f"(d[27]), "+f"(d[28]), "+f"(d[29]), "+f"(d[30]), "+f"(d[31]),
        "+f"(d[32]), "+f"(d[33]), "+f"(d[34]), "+f"(d[35]), "+f"(d[36]), "+f"(d[37]), "+f"(d[38]), "+f"(d[39])
      : "r"(da), "n"(HA), "r"(db), "n"(HB), "r"(sc));
  }
};
template <> struct WgSST<192> {
  template <uint32_t HA, uint32_t HB>
  static __device__ __forceinline__ void mma(float* d, uint32_t da, uint32_t db, int sc) {
    asm volatile("{\n.reg .pred p;\n.reg .b64 da, db;\nsetp.ne.b32 p, %100, 0;\n"
      "mov.b64 da, {%96, %97};\nmov.b64 db, {%98, %99};\n"
      "wgmma.mma_async.sync.aligned.m64n192k16.f32.bf16.bf16 {"
      "%0, %1, %2, %3, %4, %5, %6, %7, %8, %9, %10, %11, %12, %13, %14, %15, "
      "%16, %17, %18, %19, %20, %21, %22, %23, %24, %25, %26, %27, %28, %29, %30, %31, "
      "%32, %33, %34, %35, %36, %37, %38, %39, %40, %41, %42, %43, %44, %45, %46, %47, "
      "%48, %49, %50, %51, %52, %53, %54, %55, %56, %57, %58, %59, %60, %61, %62, %63, "
      "%64, %65, %66, %67, %68, %69, %70, %71, %72, %73, %74, %75, %76, %77, %78, %79, "
      "%80, %81, %82, %83, %84, %85, %86, %87, %88, %89, %90, %91, %92, %93, %94, %95"
      "}, da, db, p, 1, 1, 0, 1;\n}\n"
      : "+f"(d[0]), "+f"(d[1]), "+f"(d[2]), "+f"(d[3]), "+f"(d[4]), "+f"(d[5]), "+f"(d[6]), "+f"(d[7]),
        "+f"(d[8]), "+f"(d[9]), "+f"(d[10]), "+f"(d[11]), "+f"(d[12]), "+f"(d[13]), "+f"(d[14]), "+f"(d[15]),
        "+f"(d[16]), "+f"(d[17]), "+f"(d[18]), "+f"(d[19]), "+f"(d[20]), "+f"(d[21]), "+f"(d[22]), "+f"(d[23]),
        "+f"(d[24]), "+f"(d[25]), "+f"(d[26]), "+f"(d[27]), "+f"(d[28]), "+f"(d[29]), "+f"(d[30]), "+f"(d[31]),
        "+f"(d[32]), "+f"(d[33]), "+f"(d[34]), "+f"(d[35]), "+f"(d[36]), "+f"(d[37]), "+f"(d[38]), "+f"(d[39]),
        "+f"(d[40]), "+f"(d[41]), "+f"(d[42]), "+f"(d[43]), "+f"(d[44]), "+f"(d[45]), "+f"(d[46]), "+f"(d[47]),
        "+f"(d[48]), "+f"(d[49]), "+f"(d[50]), "+f"(d[51]), "+f"(d[52]), "+f"(d[53]), "+f"(d[54]), "+f"(d[55]),
        "+f"(d[56]), "+f"(d[57]), "+f"(d[58]), "+f"(d[59]), "+f"(d[60]), "+f"(d[61]), "+f"(d[62]), "+f"(d[63]),
        "+f"(d[64]), "+f"(d[65]), "+f"(d[66]), "+f"(d[67]), "+f"(d[68]), "+f"(d[69]), "+f"(d[70]), "+f"(d[71]),
        "+f"(d[72]), "+f"(d[73]), "+f"(d[74]), "+f"(d[75]), "+f"(d[76]), "+f"(d[77]), "+f"(d[78]), "+f"(d[79]),
        "+f"(d[80]), "+f"(d[81]), "+f"(d[82]), "+f"(d[83]), "+f"(d[84]), "+f"(d[85]), "+f"(d[86]), "+f"(d[87]),
        "+f"(d[88]), "+f"(d[89]), "+f"(d[90]), "+f"(d[91]), "+f"(d[92]), "+f"(d[93]), "+f"(d[94]), "+f"(d[95])
      : "r"(da), "n"(HA), "r"(db), "n"(HB), "r"(sc));
  }
};

struct FftConst {
  uint32_t f[2][4], fi[4][4];
  uint32_t ta[2][2], tb[2][2];
};
__device__ __forceinline__ void cis(int m, float scale, float& c, float& s) {
  const float a = (float)m * (-6.283185307179586f * scale);
  c = __cosf(a);
  s = __sinf(a);
}
__device__ __forceinline__ void fft_tables(uint32_t (&v)[12], int tw) {
  const int row = tw >> 2, ch = tw & 3;
#pragma unroll
  for (int i = 0; i < 4; i++) {
    float c[2], s[2], x[2];
#pragma unroll
    for (int e = 0; e < 2; e++) {
      cis((((32 * (8 * ch + 2 * i + e) + 15) * (4 * row - 63) + 2048) & 4095) - 2048, 1.f / 4096, c[e], s[e]);
      float gc, gs;
      cis((((row & 15) * (8 * (ch & 1) + 2 * i + e) + 8) & 15) - 8, 1.f / 16, gc, gs);
      x[e] = (row >> 4) == (ch >> 1) ? gc : (ch >> 1) ? gs : -gs;
    }
    v[i] = pack2(c[0] * 0.125f, c[1] * 0.125f);
    v[4 + i] = pack2(s[0] * 0.125f, s[1] * 0.125f);
    v[8 + i] = pack2(x[0], x[1]);
  }
#pragma unroll
  for (int i = 0; i < 12; i++) asm volatile("" : "+r"(v[i]));
}
__device__ __forceinline__ void fft_tables_store(const uint32_t (&v)[12], uint32_t sb, int tw) {
  const int row = tw >> 2;
  const uint32_t x = ((tw ^ (row >> 1)) & 3) << 4, a = sb + OFF_FT + (16 * (row >> 3) + (row & 7)) * 64 + x;
  sts128(a, v[0], v[1], v[2], v[3]);
  sts128(a + 512, v[4], v[5], v[6], v[7]);
  sts128(sb + OFF_GT + row * 64 + x, v[8], v[9], v[10], v[11]);
}
__device__ __forceinline__ void fft_twiddles(uint32_t (&v)[2], int tw) {
  float a[2], s[2];
#pragma unroll
  for (int i = 0; i < 2; i++) {
    float c;
    cis((2 * (2 * (tw & 3) + i) - 15) * (4 * (tw >> 2) - 63), 1.f / 4096, c, s[i]);
    a[i] = __fdividef(-s[i], 1.f + c);
  }
  v[0] = pack2(a[0], a[1]);
  v[1] = pack2(s[0], s[1]);
  asm volatile("" : "+r"(v[0]), "+r"(v[1]));
}
__device__ __forceinline__ void fft_matrices(FftConst& k, uint32_t sb, int w, int lane) {
  const uint32_t x = (lane >> 1) & 3;
  const uint2 t0 = lds64(sb + OFF_TT + 256 * w + 8 * lane), t1 = lds64(sb + OFF_TT + 256 * w + 8 * (lane ^ 3));
  k.ta[0][0] = t0.x;
  k.tb[0][0] = t0.y;
  k.ta[1][1] = __byte_perm(t1.x, 0, 0x1032);
  k.tb[1][1] = __byte_perm(t1.y, 0, 0x1032);
#pragma unroll
  for (int j = 0; j < 2; j++) {
    k.ta[1 - j][j] = k.ta[j][j] ^ 0x80008000u;
    k.tb[1 - j][j] = k.tb[j][j] ^ 0x80008000u;
    asm volatile("" : "+r"(k.ta[0][j]), "+r"(k.tb[0][j]), "+r"(k.ta[1][j]), "+r"(k.tb[1][j]));
  }
#pragma unroll
  for (int i = 0; i < 2; i++) {
    ldsm4(k.f[i], sb + OFF_FT + (16 * w + (lane & 15)) * 64 + (((2 * i + (lane >> 4)) ^ x) << 4));
    ldsm4t(k.fi[i], sb + OFF_FT + (32 * i + lane) * 64 + ((w ^ x) << 4));
#pragma unroll
    for (int j = 0; j < 4; j++) {
      k.fi[2 + i][j] = (j & 1) ? k.fi[i][j - 1] ^ 0x80008000u : k.fi[i][j + 1];
      asm volatile("" : "+r"(k.fi[2 + i][j]));
    }
  }
}
__device__ __forceinline__ void rot(uint32_t& x, uint32_t& y, uint32_t a, uint32_t b) {
  x = bfma(a, y, x);
  y = bfma(b, x, y);
  x = bfma(a, y, x);
}
__device__ __forceinline__ void twiddle_fwd(uint32_t (&a)[4][4], float* d, const FftConst& k) {
#pragma unroll
  for (int q = 0; q < 4; q++)
#pragma unroll
    for (int j = 0; j < 2; j++) {
      const float* x = d + 8 * q + 4 * j;
      uint32_t re = pack2(x[0], x[1]), im = pack2(x[2], x[3]);
      rot(re, im, k.ta[0][j], k.tb[0][j]);
      a[q & 2][2 * j + (q & 1)] = re;
      a[(q & 2) + 1][2 * j + (q & 1)] = im;
    }
}
__device__ __forceinline__ void g_step(float* d, const uint32_t (&a)[4][4], uint32_t dre, uint32_t dim) {
  WgRS<32>::set<HI_SW64>(d, a[0], dre);
  WgRS<32>::set<HI_SW64>(d + 16, a[2], dre);
  WgRS<32>::mma<HI_SW64>(d, a[1], dim);
  WgRS<32>::mma<HI_SW64>(d + 16, a[3], dim);
  wg_commit();
}

__device__ __forceinline__ void conv_channel(const FftConst& k, uint32_t sb, int c, int wg, int w, int lane) {
  const uint32_t cb = sb + off_ch(c), bars = sb + OFF_BAR;
  const uint32_t du = desc_lo(cb, 1024), dg = desc_lo(sb + OFF_GT, 16), dz = desc_lo(cb + U_BYTES, 16);
  float U[32], H[32];
  uint32_t a[4][4], e[4][4];
  const float dv = __uint_as_float(lds32(sb + OFF_D + 4 * c));
  wg_fence();
  WgRS<64>::set<HI_SW32>(H, k.f[0], du + 256);
  WgRS<64>::mma<HI_SW32>(H, k.f[1], du + 256 + 32);
  wg_commit();
  wg_wait<0>();
  pin<32>(H);
  twiddle_fwd(a, H, k);
  if (ATT_GATE) mbar_wait(bars + 8 * (ATT_GATE == 1 ? B_ATTN : B_ATT2), 0);
  mbar_wait(bars + 8 * (B_U + (c < 3 ? c : 3)), 0);
  TSM(w == 0 && c < 3, 7 + wg);
  wg_fence();
  WgRS<64>::set<HI_SW32>(U, k.f[0], du);
  WgRS<64>::mma<HI_SW32>(U, k.f[1], du + 32);
  wg_commit();
  g_step(H, a, dg, dg + 64);
  wg_wait<1>();
  pin<32>(U);
  twiddle_fwd(e, U, k);
  wg_fence();
  g_step(U, e, dg, dg + 64);
  wg_wait<0>();
  pin<32>(U);
  pin<32>(H);
#pragma unroll
  for (int j = 0; j < 2; j++) {
    float pr[4][2], pi[4][2];
#pragma unroll
    for (int x = 0; x < 2; x++) {
      H[4 * j + x] += dv;
#pragma unroll
      for (int m = 0; m < 4; m++) {
#pragma unroll
        for (int q = 0; q <= m; q++) {
          const int ih = 16 * (q >> 1) + 2 * (q & 1) + 4 * j + x, iu = 16 * ((m - q) >> 1) + 2 * ((m - q) & 1) + 4 * j + x;
          pr[m][x] = q ? fmaf(H[ih], U[iu], pr[m][x]) : H[ih] * U[iu];
          pi[m][x] = q ? fmaf(H[ih], U[iu + 8], pi[m][x]) : H[ih] * U[iu + 8];
          pr[m][x] = fmaf(-H[ih + 8], U[iu + 8], pr[m][x]);
          pi[m][x] = fmaf(H[ih + 8], U[iu], pi[m][x]);
        }
      }
    }
#pragma unroll
    for (int m = 0; m < 4; m++) {
      a[m & 2][2 * j + (m & 1)] = pack2(pr[m][0], pr[m][1]);
      a[(m & 2) + 1][2 * j + (m & 1)] = pack2(pi[m][0], pi[m][1]);
    }
  }
  wg_fence();
  g_step(U, a, dg + 64, dg);
  const uint32_t za = cb + U_BYTES + (8 * w + (lane & 7)) * 128 + (((lane >> 3) ^ (lane & 7)) << 4);
  const uint32_t ya = cb + (lane >> 4) * 1024 + (8 * w + (lane & 7)) * 32 + ((((lane >> 3) ^ (lane >> 2)) & 1) << 4);
  wg_sync(1 + wg);
  wg_wait<0>();
  pin<32>(U);
  TSIF(w == 0, 80 + c);
#pragma unroll
  for (int p = 0; p < 2; p++) {
#pragma unroll
    for (int i = 0; i < 4; i++) {
      const int j = i & 1;
      const float* x = U + 16 * p + 4 * j + (i & 2);
      e[p][i] = pack2(x[8], x[9]);
      e[2 + p][i] = pack2(x[0], x[1]);
      rot(e[p][i], e[2 + p][i], k.ta[1][j], k.tb[1][j]);
    }
    stsm4(za ^ (64 * p), e[p]);
    stsm4((za ^ (64 * p)) + 4096, e[2 + p]);
  }
  fence_async_smem();
  wg_sync(1 + wg);
  wg_fence();
  WgRS<64>::set<HI_SW128>(H, k.fi[0], dz);
#pragma unroll
  for (int ks = 1; ks < 4; ks++) WgRS<64>::mma<HI_SW128>(H, k.fi[ks], dz + 128 * ks);
  wg_commit();
  if (WO_FAST) mbar_wait(bars + 8 * B_ATTN, 0);
  wg_wait<0>();
  pin<32>(H);
  TSIF(w == 0, 88 + c);
#pragma unroll
  for (int j = 0; j < 8; j++)
    a[j >> 2][j & 3] = j < 2 ? pack2(H[4 * j], H[4 * j + 1]) : pack2(H[4 * j] + H[4 * j - 6], H[4 * j + 1] + H[4 * j - 5]);
  stsm4(ya, a[0]);
  stsm4(ya + 2048, a[1]);
  fence_async_smem();
  __syncwarp();
}

__device__ __forceinline__ void prep_slab(uint4* res, const uint2* sw, uint32_t sb, int slab, int w, int lane) {
  const int t = lane & 3, tp = (lane & 7) >> 1, pos = 8 * tp + 2 * (((lane >> 3) + tp) & 3) + (lane & 1);
  const uint32_t base = sb + OFF_KVS + slab * KVS_BYTES + pos * 128;
  uint32_t kk[2][4][4], vv[2][4];
  mbar_wait(sb + OFF_BAR + 8 * (B_KV + slab), 0);
#pragma unroll
  for (int h = 0; h < 2; h++) {
#pragma unroll
    for (int j = 0; j < 4; j++) {
      const uint32_t a = base + 128 * j;
      ldsm4t(kk[h][j], a + (((w + 4 * h) ^ ((a >> 7) & 7)) << 4));
    }
    const uint32_t a = base + KVS_V;
    ldsm4t(vv[h], a + (((w + 4 * h) ^ ((a >> 7) & 7)) << 4));
  }
#pragma unroll
  for (int h = 0; h < 2; h++) {
    uint32_t (&k)[4][4] = kk[h];
    uint32_t (&v)[4] = vv[h];
    const uint32_t w0 = __byte_perm(sw[h].x, 0, 0x1010), w1 = __byte_perm(sw[h].x, 0, 0x3232);
    const uint32_t w2 = __byte_perm(sw[h].y, 0, 0x1010), w3 = __byte_perm(sw[h].y, 0, 0x3232);
#pragma unroll
    for (int m = 0; m < 4; m++)
      v[m] = bmul(badd(badd(badd(bmul(k[0][m], w3), bmul(k[1][m], w2)), bmul(k[2][m], w1)), bmul(k[3][m], w0)), v[m]);
    uint32_t a[4];
#pragma unroll
    for (int m = 0; m < 4; m++) a[m] = (t & 1) ? v[(m + 3) & 3] : v[m];
    res[h] = (t & 2) ? make_uint4(a[2], a[3], a[0], a[1]) : make_uint4(a[0], a[1], a[2], a[3]);
  }
}

__device__ __forceinline__ void prep_gate(const Params& p, uint32_t sb, int b, int w, int lane) {
  uint2 gw[5], x[4][5];
#pragma unroll
  for (int j = 0; j < 5; j++) gw[j] = ldg64(reinterpret_cast<const uint2*>(p.gate_w) + lane + 32 * j);
#pragma unroll
  for (int i = 0; i < 4; i++)
#pragma unroll
    for (int j = 0; j < 5; j++)
      x[i][j] = ldg64(reinterpret_cast<const uint2*>(p.q) + (16 * b + 4 * w + i) * (DIM / 4) + lane + 32 * j);
  float s[4];
#pragma unroll
  for (int i = 0; i < 4; i++) {
    s[i] = 0.f;
#pragma unroll
    for (int j = 0; j < 5; j++) {
      const uint32_t m0 = bmul(x[i][j].x, gw[j].x), m1 = bmul(x[i][j].y, gw[j].y);
      s[i] += (bf_lo(m0) + bf_hi(m0)) + (bf_lo(m1) + bf_hi(m1));
    }
  }
  const bool h = lane & 16, q = lane & 8;
  const float a = (h ? s[2] : s[0]) + __shfl_xor_sync(0xffffffffu, h ? s[0] : s[2], 16);
  const float c = (h ? s[3] : s[1]) + __shfl_xor_sync(0xffffffffu, h ? s[1] : s[3], 16);
  float z = (q ? c : a) + __shfl_xor_sync(0xffffffffu, q ? a : c, 8);
#pragma unroll
  for (int o = 4; o > 0; o >>= 1) z += __shfl_xor_sync(0xffffffffu, z, o);
  z = bf_lo(pack2(z, 0.f));
  z = bf_lo(pack2(__fdividef(1.f, 1.f + __expf(-z)), 0.f));
  if (G_TMA) {
    mbar_wait(sb + OFF_BAR + 8 * B_S3, 0);
    if ((lane & 7) == 0) asm volatile("st.shared.f32 [%0], %1;" ::"r"(sb + OFF_GATE + 64 * (b & 7) + 16 * w + (lane >> 1)), "f"(z) : "memory");
    fence_async_smem();
  } else if ((lane & 7) == 0) {
    g_gate[16 * b + 4 * w + (lane >> 3)] = z;
  }
}

__device__ __forceinline__ uint32_t bmax(uint32_t a, uint32_t b) {
  uint32_t d;
  asm("max.bf16x2 %0, %1, %2;" : "=r"(d) : "r"(a), "r"(b));
  return d;
}
__device__ __forceinline__ void softmax_two(const float (&l)[2][2], uint32_t& p0, uint32_t& p1) {
  constexpr float kScale = 0.22360679774997896f, kLog2e = 1.4426950408889634f;
  const uint32_t r0 = pack2(l[0][0], l[1][0]), r1 = pack2(l[0][1], l[1][1]);
  const uint32_t x0 = pack2(bf_lo(r0) * kScale, bf_hi(r0) * kScale), x1 = pack2(bf_lo(r1) * kScale, bf_hi(r1) * kScale);
  uint32_t m = bmax(x0, x1);
  m = bmax(m, __shfl_xor_sync(0xffffffffu, m, 1));
  m = bmax(m, __shfl_xor_sync(0xffffffffu, m, 2));
  const float m0 = bf_lo(m) * kLog2e, m1 = bf_hi(m) * kLog2e;
  p0 = pack2(ex2(bf_lo(x0) * kLog2e - m0), ex2(bf_lo(x1) * kLog2e - m0));
  p1 = pack2(ex2(bf_hi(x0) * kLog2e - m1), ex2(bf_hi(x1) * kLog2e - m1));
}

__device__ __forceinline__ void halo_read(uint32_t (&kpv)[10], uint32_t (&vpv)[10], uint32_t (&tg)[7], const uint4* hp) {
#pragma unroll
  for (int j = 0; j < 7; j++) {
    uint32_t x0, x1, x2;
    asm volatile("ld.relaxed.gpu.global.v4.u32 {%0, %1, %2, %3}, [%4];"
                 : "=r"(x0), "=r"(x1), "=r"(x2), "=r"(tg[j]) : "l"(hp + 32 * j) : "memory");
    if (j < 4) kpv[3 * j] = x0; else vpv[3 * j - 10] = x0;
    if (j < 3) kpv[3 * j + 1] = x1; else vpv[3 * j - 9] = x1;
    if (j < 3) kpv[3 * j + 2] = x2; else if (j < 6) vpv[3 * j - 8] = x2;
  }
}

template <int ROT>
__device__ __forceinline__ void pack_qkv(const float* acc, uint32_t (&qlo)[10], uint32_t (&qhi)[10], uint32_t (&klo)[10],
                                         uint32_t (&khi)[10], uint32_t (&vlo)[10], uint32_t (&vhi)[10]) {
#pragma unroll
  for (int j = 0; j < 10; j++) {
    const int x = (j + ROT) % 10, tq = x < 8 ? x : 16 + x, tk = x < 8 ? 8 + x : 18 + x, tv = x < 8 ? 16 + x : 20 + x;
    khi[j] = pack2(acc[4 * tk + 2], acc[4 * tk + 3]);
    vhi[j] = movm(pack2(acc[4 * tv + 2], acc[4 * tv + 3]));
    qlo[j] = pack2(acc[4 * tq], acc[4 * tq + 1]);
    qhi[j] = pack2(acc[4 * tq + 2], acc[4 * tq + 3]);
    klo[j] = pack2(acc[4 * tk], acc[4 * tk + 1]);
    vlo[j] = pack2(acc[4 * tv], acc[4 * tv + 1]);
    asm volatile("" : "+r"(khi[j]), "+r"(qlo[j]), "+r"(qhi[j]), "+r"(klo[j]), "+r"(vlo[j]));
  }
}

template <int ROT> __device__ __forceinline__ void halo_send(const float* acc, uint4* ho, uint32_t tag) {
#pragma unroll
  for (int j = 0; j < 7; j++) {
    uint32_t x[3];
#pragma unroll
    for (int e = 0; e < 3; e++) {
      const int i = 3 * j + e, y = (i % 10 + ROT) % 10, tk = y < 8 ? 8 + y : 18 + y, tv = y < 8 ? 16 + y : 20 + y;
      x[e] = i < 10 ? pack2(acc[4 * tk + 2], acc[4 * tk + 3]) : i < 20 ? movm(pack2(acc[4 * tv + 2], acc[4 * tv + 3])) : 0u;
    }
    asm volatile("st.relaxed.gpu.global.v4.u32 [%0], {%1, %2, %3, %4};" ::"l"(ho + 32 * j), "r"(x[0]), "r"(x[1]), "r"(x[2]), "r"(tag) : "memory");
  }
}

__device__ __forceinline__ void attention(float* acc, uint32_t sb, int b, int par, int w, int lane, uint32_t tag, uint32_t zero) {
  const int g = lane >> 2, t = lane & 3;
  uint32_t klo[10], khi[10], vlo[10], vhi[10], qlo[10], qhi[10], kpv[10], vpv[10];
  if (HALO_FIRST && w == 3 && b < NCTA - 8) {
    uint4* ho = g_halo + (b * 2 + par) * 224 + lane;
    if (tail_first(b & 7)) halo_send<8>(acc, ho, tag);
    else halo_send<0>(acc, ho, tag);
    TSIF(par == 0, 76);
    pin<120>(acc);
  }
  if (tail_first(b & 7)) pack_qkv<8>(acc, qlo, qhi, klo, khi, vlo, vhi);
  else pack_qkv<0>(acc, qlo, qhi, klo, khi, vlo, vhi);
  const uint32_t xa = sb + OFF_KVX + (par * 3) * 2560 + lane * 16;
  if (w < 3) {
    sts128(xa + w * 2560, khi[0], khi[1], khi[2], khi[3]);
    sts128(xa + w * 2560 + 512, khi[4], khi[5], khi[6], khi[7]);
    sts128(xa + w * 2560 + 1024, khi[8], khi[9], vhi[0], vhi[1]);
    sts128(xa + w * 2560 + 1536, vhi[2], vhi[3], vhi[4], vhi[5]);
    sts128(xa + w * 2560 + 2048, vhi[6], vhi[7], vhi[8], vhi[9]);
  } else if (!HALO_FIRST && b < NCTA - 8) {
    uint4* ho = g_halo + (b * 2 + par) * 224 + lane;
#pragma unroll
    for (int j = 0; j < 7; j++) {
      const uint32_t x0 = j < 4 ? khi[3 * j] : vhi[3 * j - 10], x1 = j < 3 ? khi[3 * j + 1] : vhi[3 * j - 9];
      const uint32_t x2 = j < 3 ? khi[3 * j + 2] : j < 6 ? vhi[3 * j - 8] : 0u;
      asm volatile("st.relaxed.gpu.global.v4.u32 [%0], {%1, %2, %3, %4};" ::"l"(ho + 32 * j), "r"(x0), "r"(x1), "r"(x2), "r"(tag) : "memory");
    }
  }
  TSIF(par == 0 && w == 1, 64);
  TSIF(par == 0 && w == 3 && !HALO_FIRST, 76);
#pragma unroll
  for (int j = 0; j < 10; j++) vlo[j] = movm(vlo[j]);
  const bool far0 = 2 * t > g, far1 = 2 * t + 1 > g;
  const uint32_t mfar = (far0 ? 0x0000FFFFu : 0u) | (far1 ? 0xFFFF0000u : 0u);
  float slo[4][2], shi[4][2], lg[2][2];
  uint32_t phi[4], plo[4], qml[4], qmh[4];
#pragma unroll
  for (int h = 0; h < 4; h++) {
    const int f = h == 0 ? 0 : h == 1 ? 3 : h == 2 ? 5 : 8, hf = h < 2 ? 2 : 7;
    const bool mine = (h & 1) ? t >= 2 : t < 2;
    qml[h] = mine ? qlo[hf] : 0u;
    qmh[h] = mine ? qhi[hf] : 0u;
    float a[4] = {0.f, 0.f, 0.f, 0.f}, c[4] = {0.f, 0.f, 0.f, 0.f};
    mma16816(a, qlo[f], qhi[f], qlo[f + 1], qhi[f + 1], klo[f], klo[f + 1]);
    mma16816(c, qlo[f], qhi[f], qlo[f + 1], qhi[f + 1], khi[f], khi[f + 1]);
    mma1688(a, qml[h], qmh[h], klo[hf]);
    mma1688(c, qml[h], qmh[h], khi[hf]);
    slo[h][0] = a[0];
    slo[h][1] = a[1];
    shi[h][0] = lg[h & 1][0] = far0 ? a[2] : c[2];
    shi[h][1] = lg[h & 1][1] = far1 ? a[3] : c[3];
    if (!ATT_MERGE && (h & 1)) softmax_two(lg, phi[h - 1], phi[h]);
  }
  TSIF(par == 0 && w == 1, 65);
  if (ATT_GATE == 3 && lane == 0) mbar_arrive(sb + OFF_BAR + 8 * B_ATT2 + (phi[3] & zero));
  wg_sync(1 + par);
  TSIF(par == 0 && w == 1, 66);
  const bool nohist = (w == 0) && (b < 8);
  const uint4* hp = g_halo + ((b - 8) * 2 + par) * 224 + lane;
  uint32_t tg[7];
  if (w > 0) {
    const uint4 v0 = lds128(xa + (w - 1) * 2560), v1 = lds128(xa + (w - 1) * 2560 + 512), v2 = lds128(xa + (w - 1) * 2560 + 1024);
    const uint4 v3 = lds128(xa + (w - 1) * 2560 + 1536), v4 = lds128(xa + (w - 1) * 2560 + 2048);
    kpv[0] = v0.x; kpv[1] = v0.y; kpv[2] = v0.z; kpv[3] = v0.w; kpv[4] = v1.x; kpv[5] = v1.y; kpv[6] = v1.z; kpv[7] = v1.w;
    kpv[8] = v2.x; kpv[9] = v2.y; vpv[0] = v2.z; vpv[1] = v2.w; vpv[2] = v3.x; vpv[3] = v3.y; vpv[4] = v3.z; vpv[5] = v3.w;
    vpv[6] = v4.x; vpv[7] = v4.y; vpv[8] = v4.z; vpv[9] = v4.w;
  } else if (nohist) {
#pragma unroll
    for (int j = 0; j < 10; j++) kpv[j] = vpv[j] = 0u;
  } else {
    TSIF(par == 0, 77);
    halo_read(kpv, vpv, tg, hp);
  }
  if (w == 0 && !nohist) {
    int spins = 0;
    while (true) {
      bool ok = true;
#pragma unroll
      for (int j = 0; j < 7; j++) ok = ok && tg[j] == tag;
      if (__all_sync(0xffffffffu, ok) || ++spins > SPIN_LIMIT) break;
      halo_read(kpv, vpv, tg, hp);
    }
    TSIF(par == 0, 79);
  }
#pragma unroll
  for (int h = 0; h < 4; h++) {
    const int f = h == 0 ? 0 : h == 1 ? 3 : h == 2 ? 5 : 8, hf = h < 2 ? 2 : 7;
    float a[4] = {0.f, 0.f, 0.f, 0.f};
    mma16816(a, qlo[f], qhi[f], qlo[f + 1], qhi[f + 1], kpv[f], kpv[f + 1]);
    mma1688(a, qml[h], qmh[h], kpv[hf]);
    const float ninf = __int_as_float(0xff800000);
    lg[h & 1][0] = far0 ? (nohist ? ninf : a[0]) : slo[h][0];
    lg[h & 1][1] = far1 ? (nohist ? ninf : a[1]) : slo[h][1];
    if (h & 1) {
      softmax_two(lg, plo[h - 1], plo[h]);
      if (ATT_MERGE) {
        const float lh[2][2] = {{shi[h - 1][0], shi[h - 1][1]}, {shi[h][0], shi[h][1]}};
        softmax_two(lh, phi[h - 1], phi[h]);
      }
    }
  }
  TSIF(par == 0 && w <= 1, 67 + w);
  if (ATT_GATE == 2 && lane == 0) mbar_arrive(sb + OFF_BAR + 8 * B_ATT2 + (plo[3] & zero));
  uint32_t ov[20];
#pragma unroll
  for (int hp = 0; hp < 2; hp++) {
    const int hf = hp ? 7 : 2;
    float sh[4] = {0.f, 0.f, 0.f, 0.f}, i0 = 0.f, i1 = 0.f;
#pragma unroll
    for (int e = 0; e < 2; e++) {
      const int h = 2 * hp + e, f = h == 0 ? 0 : h == 1 ? 3 : h == 2 ? 5 : 8;
      const uint32_t a0 = plo[h] & mfar, a2 = plo[h] & ~mfar, a3 = phi[h] & mfar, c1 = phi[h] & ~mfar;
      float sum[4] = {0.f, 0.f, 0.f, 0.f};
      mma1688(sum, plo[h], phi[h], 0x3F803F80u);
      const float r0 = rcp(sum[0]), r1 = rcp(sum[2]);
#pragma unroll
      for (int j = f; j < f + 2; j++) {
        float o[4] = {0.f, 0.f, 0.f, 0.f};
        mma16816(o, a0, 0u, a2, a3, vpv[j], vlo[j]);
        mma1688(o, 0u, c1, vhi[j]);
        ov[2 * j] = pack2(o[0] * r0, o[1] * r0);
        ov[2 * j + 1] = pack2(o[2] * r1, o[3] * r1);
      }
      const bool mine = e ? g >= 4 : g < 4;
      mma16816(sh, a0, 0u, a2, a3, mine ? vpv[hf] : 0u, mine ? vlo[hf] : 0u);
      mma1688(sh, 0u, c1, mine ? vhi[hf] : 0u);
      if (e == 0 || t >= 2) {
        i0 = r0;
        i1 = r1;
      }
    }
    ov[2 * hf] = pack2(sh[0] * i0, sh[1] * i0);
    ov[2 * hf + 1] = pack2(sh[2] * i1, sh[3] * i1);
  }
  if (ATT_GATE == 4 && lane == 0) mbar_arrive(sb + OFF_BAR + 8 * B_ATT2 + (ov[19] & zero));
  TS(32 + 4 * par + w);
  mbar_wait(sb + OFF_BAR + 8 * B_P1, 0);
  const uint32_t oa = sb + OFF_OA + (lane >> 4) * 2048 + (32 * w + 2 * (lane & 15) + par) * 16;
#pragma unroll
  for (int j = 0; j < 5; j++) stsm4(oa + 4096 * j, ov + 4 * j);
  TSIF(par == 0 && w == 0, 120);
  fence_async_smem();
  TSIF(par == 0 && w == 0, 121);
  __syncwarp();
  if (lane == 0) mbar_arrive(sb + OFF_BAR + 8 * B_ATTN);
  TSM(w == 0 || w == 2, 122 + par + (w == 2 ? 3 : 0));
}

struct Maps {
  CUtensorMap x, wm, wt, k, v, y, wo, qm, qt, om, ot, u;
};

__device__ __forceinline__ void load_stage(uint32_t sb, int kb, int b, const Maps& m) {
  const uint32_t st = sb + (kb & 3) * STAGE_BYTES, bar = sb + OFF_BAR + 8 * (B_FULL1 + (kb & 3));
  const int r = b >> 3, hg = b & 7, slab = kb - KV_KB;
  const bool kv = slab >= 0 && slab < 5;
  const uint32_t kbar = sb + OFF_BAR + 8 * (B_KV + slab), dst = sb + OFF_KVS + slab * KVS_BYTES;
  mbar_expect_tx(bar, STAGE_BYTES);
  if (kv) mbar_expect_tx(kbar, KVS_BYTES);
  tma_3d(st, &m.x, 64 * kb, 64 * r, 0, bar);
  if (kv && KV_MIX) tma_3d(dst, &m.k, 0, 32 * (b >> 1) - 3, 2 * slab + (b & 1), kbar);
  tma_3d(st + ST_W, &m.wm, 80 * hg + (tail_first(hg) ? 16 : 0), 64 * kb, 0, bar);
  if (kv && KV_MIX) tma_3d(dst + KVS_V, &m.v, 0, 32 * (b >> 1), 2 * slab + (b & 1), kbar);
  tma_3d(st + ST_WT, &m.wt, 80 * hg + (tail_first(hg) ? 0 : 64), 64 * kb, 0, bar);
  if (kv && !KV_MIX) tma_3d(dst, &m.k, 0, 32 * (b >> 1) - 3, 2 * slab + (b & 1), kbar);
  if (kv && !KV_MIX) tma_3d(dst + KVS_V, &m.v, 0, 32 * (b >> 1), 2 * slab + (b & 1), kbar);
}

__global__ void __launch_bounds__(NTHR, 1) fused_kernel(const __grid_constant__ Maps m, const Params p) {
  extern __shared__ __align__(1024) uint8_t smem[];
  const uint32_t sb = (uint32_t)__cvta_generic_to_shared(smem);
  const uint32_t bars = sb + OFF_BAR;
  const int tid = threadIdx.x, lane = tid & 31;
  int b = blockIdx.x;
  if (BMAP == 1) b = (((b & 63) >> 3) * 2 + (b & 1)) * 8 + (((b < 64 ? 0x6521 : 0x7430) >> (4 * ((b >> 1) & 3))) & 7);
  if (BMAP == 2) b = ((b & 63) >> 2) * 8 + (((b < 64 ? 0x6521 : 0x7430) >> (4 * (b & 3))) & 7);
  if (BMAP == 3) b = (((b & 63) >> 3) * 2 + (b & 1)) * 8 + (((b < 64 ? 0x7430 : 0x6521) >> (4 * ((b >> 1) & 3))) & 7);
  if (BMAP == 4) b = (((b >> 4) * 2 + (b & 1)) * 8) + ((b >> 1) & 7);
  if (BMAP == 5) b = 127 - b;
  const int r = b >> 3, hg = b & 7;

  if (tid == T_ISSUE) {
    TSM(true, 0);
#pragma unroll
    for (int i = 0; i < 4; i++) mbar_init(bars + 8 * (B_FULL1 + i), 1);
#pragma unroll
    for (int i = 0; i < 3; i++) mbar_init(bars + 8 * (B_KV + i), 1);
    fence_async_smem();
#pragma unroll 1
    for (int kb = 0; kb <= PRE2; kb++) load_stage(sb, kb, b, m);
  } else if (tid >= T_PF && tid < T_PF + 12) {
    tm_prefetch(&m.x + (tid - T_PF));
  } else if (tid == T_INIT) {
#pragma unroll
    for (int i = 0; i < 4; i++) mbar_init(bars + 8 * (B_EMPTY1 + i), 8);
#pragma unroll
    for (int i = 0; i < 8; i++) mbar_init(bars + 8 * (B_FULL2 + i), 1);
#pragma unroll
    for (int i = 0; i < 4; i++) mbar_init(bars + 8 * (B_EMPTY2 + i), 8);
#pragma unroll
    for (int i = 0; i < 4; i++) mbar_init(bars + 8 * (B_U + i), 1);
    mbar_init(bars + 8 * B_HA, 4);
    mbar_init(bars + 8 * B_GATE, 4);
    mbar_init(bars + 8 * B_HB, 1);
    mbar_init(bars + 8 * B_KVD, 4);
    mbar_init(bars + 8 * B_QF, 1);
    mbar_init(bars + 8 * B_ATTN, 8);
    mbar_init(bars + 8 * B_ATT2, 8);
    mbar_init(bars + 8 * B_P1, 8);
    mbar_init(bars + 8 * B_C34, 1);
    mbar_init(bars + 8 * B_YRB, 1);
#pragma unroll
    for (int i = 0; i < 5; i++) mbar_init(bars + 8 * (B_YST + i), 4);
#pragma unroll
    for (int i = 0; i < 5; i++) mbar_init(bars + 8 * (B_US + i), U_TMA ? 4 : 1);
    mbar_init(bars + 8 * B_YSIG, 1);
    mbar_init(bars + 8 * B_YFULL, 1);
    mbar_init(bars + 8 * B_EPOCH, 1);
    mbar_init(bars + 8 * B_PREP, 4);
    mbar_init(bars + 8 * B_USIG, 1);
    mbar_init(bars + 8 * B_WST, 1);
#pragma unroll
    for (int i = 3; i < 5; i++) mbar_init(bars + 8 * (B_KV + i), 1);
    mbar_init(bars + 8 * B_E3, 8);
    mbar_init(bars + 8 * B_LAST, 1);
    mbar_init(bars + 8 * B_OSIG, 1);
    mbar_init(bars + 8 * B_WOP, 1);
    fence_async_smem();
  }
  const int warp = __shfl_sync(0xffffffffu, tid >> 5, 0), wg = warp >> 2, w = warp & 3;
  __syncthreads();

  if (wg == 3) {
    asm volatile("setmaxnreg.dec.sync.aligned.u32 56;");
    if (w == 0) {
      if (lane == 0) {
#pragma unroll 1
        for (int kb = 1 + PRE2; kb < 10; kb++) {
          if (kb >= 4) mbar_wait(bars + 8 * (kb == 7 ? B_E3 : B_EMPTY1 + (kb & 3)), (kb >> 3) & 1);
          TSIF(kb >= 4, 44 + kb);
          load_stage(sb, kb, b, m);
          TSIF(kb == 3, 60);
          if (kb == TRIG_KB) mbar_arrive(bars + 8 * B_LAST);
        }
        mbar_wait(bars + 8 * B_WOP, 0);
        mbar_wait(bars + 8 * WL_TRIG, 0);
        mbar_wait(bars + 8 * B_EPOCH, 0);
        flag_wait(g_cnt + C_W + 32 * hg, (lds32(sb + OFF_EPOCH) + 1) * 16);
        TS(30);
#pragma unroll 1
        for (int j = 0; j < 8; j++) {
          if (j >= 6) mbar_wait(bars + 8 * (B_EMPTY2 + j - 6), 0);
          if (j == 4) mbar_wait(bars + 8 * B_ATTN, 0);
          TSIF(j >= 6, 100 + j);
          if (RF_GATE && j == 6) mbar_wait(bars + 8 * B_YSIG, 0);
          mbar_expect_tx(bars + 8 * (B_FULL2 + j), j == 0 ? WO_BYTES : j == 5 ? O_BYTES + WO_BYTES + 512 : O_BYTES + WO_BYTES);
          bulk_load(sb + off_w(j), g_WO + (hg * 8 + step_src(hg, j)) * 800, WO_BYTES, bars + 8 * (B_FULL2 + j));
        }
        mbar_wait(bars + 8 * (B_EMPTY2 + Q_SLOT), 0);
        mbar_expect_tx(bars + 8 * B_QF, O_BYTES);
        tma_2d(sb + OFF_QS, &m.qm, 80 * hg, 128 * r, bars + 8 * B_QF);
        tma_2d(sb + OFF_QT, &m.qt, 80 * hg + 64, 128 * r, bars + 8 * B_QF);
      }
    } else if (w == 1) {
      unsigned epoch = 0;
      if (lane == 0) {
        epoch = atomicAdd(g_cnt + C_LAUNCH, 1u) / NCTA;
        asm volatile("st.shared.u32 [%0], %1;" ::"r"(sb + OFF_EPOCH), "r"(epoch) : "memory");
        mbar_arrive(bars + 8 * B_EPOCH);
        mbar_wait(bars + 8 * B_KVD, 0);
        mbar_expect_tx(bars + 8 * B_HB, 5 * 4096);
#pragma unroll 1
        for (int c = 0; c < 5; c++) {
          if (c == 3) mbar_wait(bars + 8 * B_S3, 0);
          bulk_load(sb + off_ch(c) + U_BYTES, p.ssm_k + (5 * b + c) * SEQ, 4096, bars + 8 * B_HB);
        }
#pragma unroll
        for (int c = 0; c < 4; c++) mbar_expect_tx(bars + 8 * (B_U + c), c < 3 ? U_BYTES : 2 * U_BYTES);
        const uint4* usrc = g_U + 5 * b * U_PITCH;
        mbar_wait(bars + 8 * B_USIG, 0);
        flag_wait(g_cnt + C_PREP + 32 * (b & 15), (epoch + 1) * NCTA);
        TS(23);
#pragma unroll
        for (int c = 0; c < 5; c++) {
          if (c == 3 && U_TRIM) mbar_wait(bars + 8 * (B_U + 2), 0);
          bulk_load(sb + off_ch(c), usrc + c * U_PITCH, U_BYTES, bars + 8 * (B_U + (c < 3 ? c : 3)));
          TSIF(c == 0 || c == 4, 116 + (c >> 2));
        }
      }
      epoch = __shfl_sync(0xffffffffu, epoch, 0);
      if (lane < 8) {
        const int src = (b & ~7) | step_src(hg, lane);
        mbar_wait(bars + 8 * OP_TRIG, 0);
        TS(20);
        bool seen = false;
#pragma unroll 1
        for (int spins = 0; spins < SPIN_LIMIT; spins++) {
          const bool now = !seen && (int)(flag_read(g_cnt + C_O + 32 * src) - (epoch + 1)) >= 0;
          if (now && lane >= 1 && lane < 4) bulk_load(sb + off_o(lane), g_O + src * 1280, O_BYTES, bars + 8 * (B_FULL2 + lane));
          seen = seen || now;
          if (__all_sync(0xff, seen)) break;
        }
        TS(21);
        if (lane == 5) bulk_load(sb + OFF_GATE, g_gate + 128 * r, 512, bars + 8 * (B_FULL2 + 5));
#pragma unroll 1
        for (int j = 4; j < 8; j++) {
          if (lane == j) {
            mbar_wait(bars + 8 * (j < 6 ? B_C34 : B_EMPTY2 + j - 6), 0);
            if (RF_GATE && j == 6) mbar_wait(bars + 8 * B_YSIG, 0);
            bulk_load(sb + off_o(j), g_O + src * 1280, O_BYTES, bars + 8 * (B_FULL2 + j));
          }
          __syncwarp(0xff);
        }
        TS(22);
      }
    } else if (w == 2) {
      mbar_wait(bars + 8 * B_PREP, 0);
      flag_signal(g_cnt + C_PREP, 16, lane);
      TS(25);
      if (lane == 0) mbar_arrive(bars + 8 * B_USIG);
      mbar_wait(bars + 8 * B_GATE, 0);
      if (G_TMA) {
        if (lane == 0) {
          asm volatile("cp.async.bulk.global.shared::cta.bulk_group [%0], [%1], 64;\ncp.async.bulk.commit_group;\n"
                       "cp.async.bulk.wait_group.read 0;" ::"l"(g_gate + 16 * b), "r"(sb + OFF_GATE + 64 * hg) : "memory");
          bulk_load(sb + OFF_GATE + 64 * hg, g_gate + 16 * b, 64, bars + 8 * B_ORB);
        }
      } else if (((NOMB & 1) || O_RB) && lane == 0) {
        asm volatile("fence.release.gpu;" ::: "memory");
      }
      mbar_wait(bars + 8 * B_ATTN, 0);
      if (lane == 0) {
        if (O_DEFER) mbar_wait(bars + 8 * (B_U + 3), 0);
        asm volatile("cp.async.bulk.global.shared::cta.bulk_group [%0], [%1], 20480;\ncp.async.bulk.commit_group;"
                     ::"l"(g_O + b * 1280), "r"(sb + OFF_OA) : "memory");
        if (O_RB == 2) {
          asm volatile("cp.async.bulk.wait_group.read 0;" ::: "memory");
          mbar_expect_tx(bars + 8 * B_ORB, O_BYTES + 64 * G_TMA);
          bulk_load(sb + OFF_OA, g_O + b * 1280, O_BYTES, bars + 8 * B_ORB);
          mbar_wait(bars + 8 * B_ORB, 0);
          flag_bump(g_cnt + C_O + 32 * b);
        } else if (O_RB) asm volatile("cp.async.bulk.wait_group.read 0;" ::: "memory");
        else asm volatile("cp.async.bulk.wait_group 0;\nfence.proxy.async.global;" ::: "memory");
      }
      TS(74);
      if (O_RB == 2) {
      } else if (O_RB) {
        __syncwarp();
        unsigned v[5];
#pragma unroll
        for (int c = 0; c < 5; c++) v[c] = flag_read(reinterpret_cast<const unsigned*>(g_O + b * 1280 + 256 * c + 8 * lane + 7));
        const unsigned dep = __reduce_or_sync(0xffffffffu, (v[0] ^ v[1] ^ v[2] ^ v[3] ^ v[4]) & p.zero);
        if (lane == 0) flag_bump(g_cnt + C_O + 32 * b + dep);
      } else if (!(NOMB & 1)) flag_signal(g_cnt + C_O + 32 * b, 1, lane);
      else if (lane == 0) flag_bump(g_cnt + C_O + 32 * b);
      TS(26);
      if (lane == 0) mbar_arrive(bars + 8 * B_OSIG);

    } else {
      if (lane == 0) {
        uint4* dst = g_WO + (hg * 8 + (r >> 1)) * 800 + (r & 1) * 80;
        mbar_wait(bars + 8 * B_P1, 0);
        mbar_wait(bars + 8 * WB_TRIG, 0);
        mbar_expect_tx(bars + 8 * B_WST, WO_BYTES / 2);
        tma_3d(sb + OFF_WS, &m.wo, 0, 40 * r, 5 * hg, bars + 8 * B_WST);
        mbar_wait(bars + 8 * B_WST, 0);
        mbar_wait(bars + 8 * WO_TRIG, 0);
#pragma unroll 1
        for (int n = 0; n < 5; n++)
          asm volatile("cp.async.bulk.global.shared::cta.bulk_group [%0], [%1], 1280;" ::"l"(dst + 160 * n), "r"(sb + OFF_WS + 1280 * n) : "memory");
        if (W_RB) {
          asm volatile("cp.async.bulk.commit_group;\ncp.async.bulk.wait_group.read 0;" ::: "memory");
          mbar_expect_tx(bars + 8 * B_WST, WO_BYTES / 2);
#pragma unroll 1
          for (int n = 0; n < 5; n++) bulk_load(sb + OFF_WS + 1280 * n, dst + 160 * n, 1280, bars + 8 * B_WST);
          mbar_wait(bars + 8 * B_WST, 1);
        } else {
          asm volatile("cp.async.bulk.commit_group;\ncp.async.bulk.wait_group 0;\nfence.proxy.async.global;" ::: "memory");
          if (!(NOMB & 4)) asm volatile("fence.release.gpu;" ::: "memory");
        }
        flag_bump(g_cnt + C_W + 32 * hg);
        mbar_arrive(bars + 8 * B_WOP);
        TS(71);
        mbar_expect_tx(bars + 8 * B_C34, 3 * U_BYTES);
        mbar_expect_tx(bars + 8 * B_YRB, 2 * U_BYTES);
#pragma unroll 1
        for (int c = 0; c < 5; c++) {
          mbar_wait(bars + 8 * (B_YST + c), 0);
          asm volatile("cp.async.bulk.global.shared::cta.bulk_group [%0], [%1], 4096;\ncp.async.bulk.commit_group;\n"
                       "cp.async.bulk.wait_group.read 0;" ::"l"(g_Y + (5 * b + c) * Y_PITCH), "r"(sb + off_ch(c)) : "memory");
          bulk_load(sb + off_ch(c), g_Y + (5 * b + c) * Y_PITCH, U_BYTES, bars + 8 * (c < 3 ? B_C34 : B_YRB));
        }
        TS(75);
        mbar_wait(bars + 8 * B_C34, 0);
        mbar_wait(bars + 8 * B_YRB, 0);
        flag_bump(g_cnt + C_Y + 32 * (b >> 4));
        TS(27);
        mbar_arrive(bars + 8 * B_YSIG);
        mbar_expect_tx(bars + 8 * B_YFULL, 20480);
        flag_wait(g_cnt + C_Y + 32 * hg, (lds32(sb + OFF_EPOCH) + 1) * 16);
        TS(24);
        tma_2d(sb + OFF_YT, &m.y, 128 * r, 80 * hg, bars + 8 * B_YFULL);
        tma_2d(sb + OFF_YT + 10240, &m.y, 128 * r + 64, 80 * hg, bars + 8 * B_YFULL);
      }
    }
  } else {
    asm volatile("setmaxnreg.inc.sync.aligned.u32 152;");
    if (wg < 2) {
      float acc[120];
#pragma unroll
      for (int i = 0; i < 120; i++) acc[i] = 0.f;
      const uint32_t da = desc_lo(sb + wg * 8192, 16), db = desc_lo(sb + ST_W, 8192), dc = desc_lo(sb + ST_WT, 2048);
      if (PW1) pin<120>(acc);
      if (PW1 == 2) mbar_wait(bars + 8 * B_FULL1, 0);
#pragma unroll 1
      for (int kb = 0; kb < 10; kb++) {
        mbar_wait(bars + 8 * (B_FULL1 + (kb & 3)), (kb >> 2) & 1);
        const uint32_t so = (kb & 3) * (STAGE_BYTES >> 4);
        wg_fence();
#pragma unroll
        for (int k = 0; k < 4; k++) {
          WgSST<192>::mma<HI_SW128, HI_SW128>(acc, da + so + 2 * k, db + so + 128 * k, 1);
          WgSST<48>::mma<HI_SW128, HI_SW32>(acc + 96, da + so + 2 * k, dc + so + 32 * k, 1);
        }
        wg_commit();
        wg_wait<1>();
        if (kb > 0 && lane == 0) mbar_arrive(bars + 8 * (kb == 4 ? B_E3 : B_EMPTY1 + ((kb - 1) & 3)));
      }
      mbar_wait(bars + 8 * B_EPOCH, 0);
      const uint32_t tag = lds32(sb + OFF_EPOCH) + 1;
      mbar_wait(bars + 8 * B_S3, 0);
      wg_wait<0>();
      pin<120>(acc);
      if (lane == 0) mbar_arrive(bars + 8 * B_P1);
      TSM(w == 0, 3 + wg);
      attention(acc, sb, b, wg, w, lane, tag, p.zero);
    } else {
      const int tw = tid & 127, chl = 64 * (b & 1) + 8 * w + (lane >> 2);
      uint4* up = g_U + chl * U_PITCH + ((4 * (b >> 1) + (lane & 3)) ^ ((b >> 2) & 1));
      uint2 sw[10];
      uint32_t dv = 0;
      if (lane < 5) dv = __ldg(reinterpret_cast<const unsigned short*>(p.ssm_D) + 5 * b + lane);
#pragma unroll
      for (int i = 0; i < 10; i++) sw[i] = ldg64(reinterpret_cast<const uint2*>(p.shift_k) + chl + 128 * (i >> 1) + 32 * (i & 1));
      uint32_t tab[12];
      uint32_t tt[2];
      fft_tables(tab, tw);
      fft_twiddles(tt, tw);
      uint4 res[10];
#pragma unroll
      for (int i = 0; i < 10; i++) res[i] = make_uint4(0, 0, 0, 0);
#pragma unroll 1
      for (int slab = 0; slab < 5; slab++) {
#pragma unroll
        for (int i = 0; i < 8; i++) res[i] = res[i + 2];
        prep_slab(res + 8, sw, sb, slab, w, lane);
        TSIF(w == 0, 99 + 4 * slab);
#pragma unroll
        for (int i = 0; i < 8; i++) sw[i] = sw[i + 2];
      }
      TSIF(w == 0, 28);
      __syncwarp();
      if (lane == 0) mbar_arrive(bars + 8 * B_KVD + ((res[8].x ^ res[9].x) & p.zero));
      mbar_wait(bars + 8 * B_KVD, 0);
      fft_tables_store(tab, sb, tw);
      mbar_wait(bars + 8 * B_LAST, 0);
#pragma unroll
      for (int i = 0; i < 10; i++) up[(128 * (i >> 1) + 32 * (i & 1)) * U_PITCH] = res[i];
      __syncwarp();
      if (lane == 0) mbar_arrive(bars + 8 * B_PREP);
      TSIF(w == 0 && !U_TMA, 5);
      mbar_wait(bars + 8 * (G_AFTER ? B_USIG : B_LAST), 0);
      prep_gate(p, sb, b, w, lane);
      __syncwarp();
      if (lane == 0) mbar_arrive(bars + 8 * B_GATE);
      TSIF(w == 0, 72);
      mbar_wait(bars + 8 * B_HB, 0);
      TSIF(w == 0, 2);
      const uint32_t ha = sb + U_BYTES + ((tw >> 3) * 16 + 8 + (tw & 7)) * 16;
      uint4 hv[5];
#pragma unroll
      for (int c = 0; c < 5; c++) hv[c] = lds128(ha + off_ch(c));
      __syncwarp();
#pragma unroll
      for (int c = 0; c < 5; c++) sts128((ha ^ 16) + off_ch(c), hv[c].x, hv[c].y, hv[c].z, hv[c].w);
      asm volatile("st.shared.v2.u32 [%0], {%1, %2};" ::"r"(sb + OFF_TT + 8 * tw), "r"(tt[0]), "r"(tt[1]) : "memory");
      if (tw < 5) asm volatile("st.shared.f32 [%0], %1;" ::"r"(sb + OFF_D + 4 * tw), "f"(bf_lo(dv) * 0.125f) : "memory");
      fence_async_smem();
      __syncwarp();
      if (lane == 0) mbar_arrive(bars + 8 * B_HA);
      TSIF(w == 0, 6);
    }

    FftConst fc;
    TSM(w == 0 && wg == 0, 104);
    mbar_wait(bars + 8 * B_HA, 0);
    fft_matrices(fc, sb, w, lane);
    TSM(w == 0 && wg == 0, 105);
    TSM(w == 0 && wg == 2, 124);
#pragma unroll 1
    for (uint32_t tasks = wg == 0 ? TASK0 : wg == 1 ? TASK1 : TASK2; tasks; tasks >>= 4) {
      const int c = (tasks & 7) - 1;
      conv_channel(fc, sb, c, wg, w, lane);
      if (lane == 0) mbar_arrive(bars + 8 * (B_YST + c));
      TSM(w == 0, 10 + c);
    }

    if (wg < 2) {
      const int g = lane >> 2;
      float acc[40];
#pragma unroll
      for (int i = 0; i < 40; i++) acc[i] = 0.f;
      const uint32_t da = desc_lo(sb + wg * 1024, 2048), db = desc_lo(sb, 2560);
      if (!WO_FAST) mbar_wait(bars + 8 * (O_RB == 2 ? B_ORB : B_ATTN), 0);
      mbar_wait(bars + 8 * (B_YST + 3), 0);
      mbar_wait(bars + 8 * (B_YST + 4), 0);
      if (PW2 && !WO_FAST) mbar_wait(bars + 8 * B_FULL2, 0);
      TSM(w == 0, 15 + wg);
#pragma unroll 1
      for (int j = 0; j < 8; j++) {
        mbar_wait(bars + 8 * (B_FULL2 + j), 0);
        const uint32_t oa = da + (off_o(j) >> 4), ob = db + (off_w(j) >> 4);
        wg_fence();
#pragma unroll
        for (int k = 0; k < 5; k++) WgSST<80>::mma<HI_NONE, HI_SW32>(acc, oa + 256 * k, ob + 32 * k, 1);
        wg_commit();
        wg_wait<1>();
        if (j >= 1 && j <= Q_SLOT + 1 && lane == 0) mbar_arrive(bars + 8 * (B_EMPTY2 + j - 1));
      }
      TSIF(w == 0 && wg == 0, 113);
      const int tr = 64 * wg + 16 * w + (lane & 15);
      const uint32_t fm = sb + OFF_QS + tr * 128, fx = (lane >> 4) ^ (tr & 7);
      const uint32_t ft = sb + OFF_QT + tr * 32 + (((lane >> 4) ^ (tr >> 2)) & 1) * 16;
      const float g0 = __uint_as_float(lds32(sb + OFF_GATE + (64 * wg + 16 * w + g) * 4));
      const float g1 = __uint_as_float(lds32(sb + OFF_GATE + (64 * wg + 16 * w + 8 + g) * 4));
      const uint32_t ga = pack2(g0, g0), gb = pack2(g1, g1);
      const uint32_t na = pack2(1.f - g0, 1.f - g0), nb = pack2(1.f - g1, 1.f - g1);

      uint32_t qf[20];
      mbar_wait(bars + 8 * B_QF, 0);
#pragma unroll
      for (int j = 0; j < 5; j++) ldsm4(qf + 4 * j, j < 4 ? fm + ((fx ^ (2 * j)) << 4) : ft);
      if (FUSE_MIX) {
#pragma unroll
        for (int i = 0; i < 20; i++) {
          qf[i] = bmul((i & 1) ? gb : ga, qf[i]);
          asm volatile("" : "+r"(qf[i]));
        }
      }
      wg_wait<0>();
      pin<40>(acc);
      TSM(w == 0, 17 + wg);
      uint32_t pb[20];
#pragma unroll
      for (int j = 0; j < 10; j++) {
        pb[2 * j] = bmul(na, pack2(acc[4 * j], acc[4 * j + 1]));
        pb[2 * j + 1] = bmul(nb, pack2(acc[4 * j + 2], acc[4 * j + 3]));
        asm volatile("" : "+r"(pb[2 * j]), "+r"(pb[2 * j + 1]));
      }
      const uint32_t ya = sb + OFF_YT + wg * 10240 + ((lane >> 4) * 8 + (lane & 7)) * 128 +
                          (((2 * w + (((lane >> 3) & 1) ^ wg)) ^ (lane & 7)) << 4);
      mbar_wait(bars + 8 * B_YFULL, 0);
      TSM(w == 0 && wg == 0, 19);
#pragma unroll
      for (int j = 0; j < 5; j++) {
        uint32_t y[4];
        ldsm4t(y, ya + 2048 * j);
#pragma unroll
        for (int i = 0; i < 4; i++)
          qf[4 * j + i] = FUSE_MIX ? bfma(qf[4 * j + i], y[i], pb[4 * j + i]) : badd(bmul((i & 1) ? gb : ga, bmul(qf[4 * j + i], y[i])), pb[4 * j + i]);
      }
#pragma unroll
      for (int j = 0; j < 5; j++) stsm4(j < 4 ? fm + ((fx ^ (2 * j)) << 4) : ft, qf + 4 * j);
      fence_async_smem();
      __syncwarp();
      if (lane == 0) {
        const int row = 64 * wg + 16 * w;
        asm volatile("cp.async.bulk.tensor.2d.global.shared::cta.bulk_group [%0, {%2, %3}], [%1];"
                     ::"l"(&m.om), "r"(sb + OFF_QS + row * 128), "r"(80 * hg), "r"(128 * r + row) : "memory");
        asm volatile("cp.async.bulk.tensor.2d.global.shared::cta.bulk_group [%0, {%2, %3}], [%1];"
                     ::"l"(&m.ot), "r"(sb + OFF_QT + row * 32), "r"(80 * hg + 64), "r"(128 * r + row) : "memory");
        asm volatile("cp.async.bulk.commit_group;\ncp.async.bulk.wait_group.read 0;" ::: "memory");
      }
      TSM(true, 40 + 4 * wg + w);
      if (ENDBAR) asm volatile("bar.sync 15, 256;" ::: "memory");
    }
  }
}

typedef CUresult (*EncodeFn)(CUtensorMap*, CUtensorMapDataType, cuuint32_t, void*, const cuuint64_t*, const cuuint64_t*,
                             const cuuint32_t*, const cuuint32_t*, CUtensorMapInterleave, CUtensorMapSwizzle,
                             CUtensorMapL2promotion, CUtensorMapFloatOOBfill);

void encode(EncodeFn fn, CUtensorMap* tm, const void* base, int rank, const cuuint64_t* dims, const cuuint64_t* strides,
            const cuuint32_t* box, CUtensorMapSwizzle swz) {
  const cuuint32_t ones[3] = {1, 1, 1};
  fn(tm, CU_TENSOR_MAP_DATA_TYPE_BFLOAT16, rank, const_cast<void*>(base), dims, strides, box, ones,
     CU_TENSOR_MAP_INTERLEAVE_NONE, swz, CU_TENSOR_MAP_L2_PROMOTION_L2_128B, CU_TENSOR_MAP_FLOAT_OOB_FILL_NONE);
}

}

extern "C" void kernel_launch(void* const* d_in, const int* in_sizes, int n_in, void* d_out, int out_size) {
  (void)in_sizes; (void)n_in; (void)out_size;
  Params p;
  p.q = (const __nv_bfloat16*)d_in[0];
  p.k = (const __nv_bfloat16*)d_in[1];
  p.v = (const __nv_bfloat16*)d_in[2];
  p.shift_k = (const __nv_bfloat16*)d_in[3];
  p.ssm_k = (const __nv_bfloat16*)d_in[4];
  p.ssm_D = (const __nv_bfloat16*)d_in[5];
  p.wqkv = (const __nv_bfloat16*)d_in[7];
  p.wo = (const __nv_bfloat16*)d_in[8];
  p.gate_w = (const __nv_bfloat16*)d_in[9];
  p.out = (__nv_bfloat16*)d_out;
  p.zero = 0;

  static EncodeFn fn = nullptr;
  static void *yaddr = nullptr, *uaddr = nullptr;
  if (!fn) {
    cudaDriverEntryPointQueryResult qr;
    void* f = nullptr;
    cudaGetDriverEntryPoint("cuTensorMapEncodeTiled", &f, cudaEnableDefault, &qr);
    fn = (EncodeFn)f;
    cudaGetSymbolAddress(&yaddr, g_Y);
    cudaGetSymbolAddress(&uaddr, g_U);
    cudaFuncSetAttribute(fused_kernel, cudaFuncAttributeMaxDynamicSharedMemorySize, SMEM_BYTES);
  }
  Maps m;
  {
    const cuuint64_t dims[3] = {640, 1024, 2}, st[2] = {2560, 1280};
    const cuuint32_t box[3] = {64, 64, 2};
    encode(fn, &m.x, p.q, 3, dims, st, box, CU_TENSOR_MAP_SWIZZLE_128B);
  }
  {
    const cuuint64_t dims[3] = {640, 640, 3}, st[2] = {3840, 1280};
    const cuuint32_t box[3] = {64, 64, 3}, boxt[3] = {16, 64, 3};
    encode(fn, &m.wm, p.wqkv, 3, dims, st, box, CU_TENSOR_MAP_SWIZZLE_128B);
    encode(fn, &m.wt, p.wqkv, 3, dims, st, boxt, CU_TENSOR_MAP_SWIZZLE_32B);
  }
  {
    const cuuint64_t dims[3] = {64, 2048, 10}, st[2] = {1280, 128};
    const cuuint32_t boxk[3] = {64, 35, 1}, boxv[3] = {64, 32, 1};
    encode(fn, &m.k, p.k, 3, dims, st, boxk, CU_TENSOR_MAP_SWIZZLE_128B);
    encode(fn, &m.v, p.v, 3, dims, st, boxv, CU_TENSOR_MAP_SWIZZLE_128B);
  }
  {
    const cuuint64_t dims[3] = {16, 640, 40}, st[2] = {1280, 32};
    const cuuint32_t box[3] = {16, 40, 5};
    encode(fn, &m.wo, p.wo, 3, dims, st, box, CU_TENSOR_MAP_SWIZZLE_32B);
  }
  {
    const cuuint64_t dims[2] = {2048, 640}, st[1] = {Y_PITCH * 16};
    const cuuint32_t box[2] = {64, 80};
    encode(fn, &m.y, yaddr, 2, dims, st, box, CU_TENSOR_MAP_SWIZZLE_128B);
    const cuuint64_t stu[1] = {U_PITCH * 16};
    const cuuint32_t boxu[2] = {32, 64};
    encode(fn, &m.u, uaddr, 2, dims, stu, boxu, CU_TENSOR_MAP_SWIZZLE_NONE);
  }
  {
    const cuuint64_t dims[2] = {640, 2048}, st[1] = {1280};
    const cuuint32_t bqm[2] = {64, 128}, bqt[2] = {16, 128}, bom[2] = {64, 16}, bot[2] = {16, 16};
    encode(fn, &m.qm, p.q, 2, dims, st, bqm, CU_TENSOR_MAP_SWIZZLE_128B);
    encode(fn, &m.qt, p.q, 2, dims, st, bqt, CU_TENSOR_MAP_SWIZZLE_32B);
    encode(fn, &m.om, p.out, 2, dims, st, bom, CU_TENSOR_MAP_SWIZZLE_128B);
    encode(fn, &m.ot, p.out, 2, dims, st, bot, CU_TENSOR_MAP_SWIZZLE_32B);
  }
  fused_kernel<<<NCTA, NTHR, SMEM_BYTES>>>(m, p);
}
```

```cpp
#include <cuda.h>
#include <cuda_bf16.h>
#include <cuda_runtime.h>
#include <stdint.h>

namespace {

constexpr int SEQ = 2048, DIM = 640, NCTA = 128, NTHR = 512;

#define TRIG_KB 9
#define KV_KB 2
#define DEV_EXIT 0
#define ATT_GATE 0
#define G_AFTER 0
#define FENCE_LO 0
#define FENCE_HI 0
#define PW1 2
#define PW2 1
#define ENDBAR 0
#define PAD_KB 0
#define Y_ALIAS 1
#define NOMB 0
#define SRC_ROT 0
#define WAIT_NS 0
#define WB_TRIG B_USIG
#define G_POS 0
#define TAILF 1
#define T_ISSUE 384
#define T_PF 416
#define T_INIT 448
#define ATT_MERGE 0
#define BMAP 1
#define PRE2 1
#define KV_MIX 0
#define O_DEFER 0
#define TASK0 0x52
#define TASK1 0x3
#define TASK2 0x41
#define HALO_FIRST 1
#define PREV_EARLY 0
#define Y_RB 2
#define O_RB 2
#define O_EAGER 1
#define OP_TRIG B_ATTN
#define FUSE_MIX 1
#define Q_EARLY 1
#define WO_FAST 0
#define U_TRIM 1
#define Q_SLOT 3
#define G_TMA 1
#define W_RB 0
#define WPF 0
#define WPF_LIN 1
#define ACQ 0
#define U_TMA 0
#define U_GATE 0
#define RF_GATE 0
#define WO_TRIG B_WST
#define WL_TRIG B_WOP
#define WO_GATE 1

constexpr uint32_t STAGE_BYTES = 47104, ST_W = 16384, ST_WT = 40960;
constexpr uint32_t O_BYTES = 20480, WO_BYTES = 12800;
constexpr uint32_t OFF_OA = 0;
constexpr uint32_t OFF_QS = Q_SLOT * O_BYTES, OFF_QT = OFF_QS + 16384;
constexpr uint32_t OFF_WC = 81920;
constexpr uint32_t OFF_WA = 94720;
constexpr uint32_t OFF_GATE = 145920;
constexpr uint32_t OFF_TT = 146432;
constexpr uint32_t OFF_KVX = 148480;
constexpr uint32_t OFF_CH3 = 163840;
constexpr uint32_t CH_BYTES = 12288, U_BYTES = 4096;
constexpr uint32_t OFF_FT = 225280, OFF_GT = 229376;
constexpr uint32_t OFF_CH0 = 188416;
constexpr uint32_t OFF_KVS = OFF_CH0, KVS_V = 4480, KVS_BYTES = 8576;
constexpr uint32_t OFF_WS = OFF_WA;
__device__ __forceinline__ uint32_t off_us(int s) { return OFF_CH0 + 4096 * ((0x65320 >> (4 * s)) & 7); }
constexpr uint32_t OFF_YT = 163840;
constexpr uint32_t OFF_BAR = 231936;
constexpr uint32_t SMEM_BYTES = OFF_BAR + 512;

enum : uint32_t {
  B_FULL1 = 0, B_EMPTY1 = 4, B_S3 = 7, B_FULL2 = 52, B_EMPTY2 = 13, B_U = 8, B_GATE = 12, B_HA = 19, B_HB = 20,
  B_ATTN = 21, B_C34 = 22, B_YRB = 23, B_YFULL = 24, B_EPOCH = 25, B_PREP = 26, B_P1 = 27, B_LAST = 28,
  B_E3 = 29, B_OSIG = 30, B_WOP = 31, B_USIG = 32, B_WST = 33, B_KV = 34, B_KVD = 39, B_QF = 17, B_ATT2 = 18, B_YST = 40,
  B_ORB = 45, B_US = 45, B_YSIG = 50
};
constexpr uint32_t OFF_EPOCH = OFF_BAR + 8 * 51, OFF_D = OFF_BAR + 8 * 60;
__device__ __forceinline__ uint32_t off_o(int j) { return j < 4 ? OFF_OA + j * O_BYTES : j < 6 ? OFF_CH0 + (j - 4) * O_BYTES : OFF_OA + (j - 6) * O_BYTES; }
__device__ __forceinline__ uint32_t off_w(int j) { return j < 4 ? OFF_WA + j * WO_BYTES : j == 4 ? OFF_KVX : j == 5 ? OFF_WC : OFF_WA + (j - 6) * WO_BYTES; }
__device__ __forceinline__ int step_src(int hg, int j) {
  if (SRC_ROT == 2) {
    const int pos = (0x37621540 >> (4 * hg)) & 7;
    return j == 0 ? hg : (0x65217430 >> (4 * (j <= pos ? j - 1 : j))) & 7;
  }
  return SRC_ROT ? (hg + j) & 7 : j == 0 ? hg : j <= hg ? j - 1 : j;
}
__device__ __forceinline__ bool tail_first(int hg) { return TAILF && (hg & 3) == 3; }
__device__ __forceinline__ uint32_t off_ch(int c) { return (c < 3 ? OFF_CH0 : OFF_CH3 - 3 * CH_BYTES) + c * CH_BYTES; }

#define U_PITCH 264
__device__ __align__(1024) uint4 g_U[DIM * U_PITCH];
__device__ uint4 g_O[NCTA * 1280];
#define g_Y g_U
constexpr int Y_PITCH = U_PITCH;
__device__ uint4 g_WO[64 * 800];
__device__ uint4 g_halo[NCTA * 2 * 7 * 32];
__device__ __align__(128) float g_gate[SEQ + PAD_KB * 256];
__device__ unsigned g_cnt[32 * (1 + 2 * 16 + 8 + NCTA)];
constexpr int C_LAUNCH = 0, C_PREP = 32, C_Y = 32 * 17, C_W = 32 * 33, C_O = 32 * 41;

#define TSM(cond, slot) do { } while (0)
#define TSIF(cond, slot) do { if (__LINE__ >= FENCE_LO && __LINE__ < FENCE_HI) sched_fence(); } while (0)
__device__ __forceinline__ void sched_fence() {
  asm volatile("{\n.reg .pred p;\n.reg .u32 c;\nmov.u32 c, %%clock;\nsetp.eq.u32 p, c, 0;\n@p st.shared.u32 [%0], c;\n}"
               ::"r"(1024 + OFF_EPOCH + 4) : "memory");
}
#define TS(slot) TSIF(true, slot)

struct Params {
  const __nv_bfloat16 *q, *k, *v, *shift_k, *ssm_k, *ssm_D, *wqkv, *wo, *gate_w;
  __nv_bfloat16* out;
  uint32_t zero;
};

#define POLL_NS 0
constexpr int SPIN_LIMIT = 1 << 17;

__device__ __forceinline__ void mbar_init(uint32_t bar, uint32_t count) {
  asm volatile("mbarrier.init.shared::cta.b64 [%0], %1;" ::"r"(bar), "r"(count) : "memory");
}
__device__ __forceinline__ void mbar_expect_tx(uint32_t bar, uint32_t bytes) {
  asm volatile("mbarrier.arrive.expect_tx.shared::cta.b64 _, [%0], %1;" ::"r"(bar), "r"(bytes) : "memory");
}
__device__ __forceinline__ void mbar_arrive(uint32_t bar) {
  asm volatile("mbarrier.arrive.shared::cta.b64 _, [%0];" ::"r"(bar) : "memory");
}
__device__ __forceinline__ void mbar_wait(uint32_t bar, uint32_t parity) {
  uint32_t ok;
  int spins = 0;
  do {
    if (WAIT_NS)
      asm volatile("{\n.reg .pred p;\nmbarrier.try_wait.parity.shared::cta.b64 p, [%1], %2, %3;\nselp.b32 %0, 1, 0, p;\n}"
                   : "=r"(ok) : "r"(bar), "r"(parity), "r"(WAIT_NS) : "memory");
    else
      asm volatile("{\n.reg .pred p;\nmbarrier.try_wait.parity.shared::cta.b64 p, [%1], %2;\nselp.b32 %0, 1, 0, p;\n}"
                   : "=r"(ok) : "r"(bar), "r"(parity) : "memory");
    if (++spins > SPIN_LIMIT) break;
  } while (!ok);
}
__device__ __forceinline__ unsigned flag_read(const unsigned* p) {
  unsigned v;
  asm volatile("ld.relaxed.gpu.global.u32 %0, [%1];" : "=r"(v) : "l"(p) : "memory");
  return v;
}
__device__ __forceinline__ void flag_poll(const unsigned* p, unsigned target) {
  unsigned v;
  int spins = 0;
  do {
    if (POLL_NS && spins) __nanosleep(POLL_NS);
    asm volatile("ld.relaxed.gpu.global.u32 %0, [%1];" : "=r"(v) : "l"(p) : "memory");
    if (++spins > SPIN_LIMIT) break;
  } while ((int)(v - target) < 0);
}
__device__ __forceinline__ void flag_wait(const unsigned* p, unsigned target) {
  flag_poll(p, target);
  if (ACQ) asm volatile("fence.acquire.gpu;\nfence.proxy.async.global;" ::: "memory");
}
__device__ __forceinline__ void flag_signal(unsigned* p, int n, int lane) {
  if (lane == 0) asm volatile("fence.release.gpu;" ::: "memory");
  __syncwarp();
  if (lane < n) asm volatile("red.relaxed.gpu.global.add.u32 [%0], 1;" ::"l"(p + 32 * lane) : "memory");
}
__device__ __forceinline__ void flag_bump(unsigned* p) {
  asm volatile("red.relaxed.gpu.global.add.u32 [%0], 1;" ::"l"(p) : "memory");
}
__device__ __forceinline__ void fence_async_smem() { asm volatile("fence.proxy.async.shared::cta;" ::: "memory"); }
__device__ __forceinline__ void wg_sync(int id) { asm volatile("bar.sync %0, 128;" ::"r"(id) : "memory"); }

__device__ __forceinline__ void tma_2d(uint32_t dst, const CUtensorMap* tm, int c0, int c1, uint32_t bar) {
  asm volatile("cp.async.bulk.tensor.2d.shared::cluster.global.mbarrier::complete_tx::bytes [%0], [%1, {%3, %4}], [%2];"
               ::"r"(dst), "l"(tm), "r"(bar), "r"(c0), "r"(c1) : "memory");
}
__device__ __forceinline__ void tma_3d(uint32_t dst, const CUtensorMap* tm, int c0, int c1, int c2, uint32_t bar) {
  asm volatile("cp.async.bulk.tensor.3d.shared::cluster.global.mbarrier::complete_tx::bytes [%0], [%1, {%3, %4, %5}], [%2];"
               ::"r"(dst), "l"(tm), "r"(bar), "r"(c0), "r"(c1), "r"(c2) : "memory");
}
__device__ __forceinline__ void bulk_load(uint32_t dst, const void* src, uint32_t bytes, uint32_t bar) {
  asm volatile("cp.async.bulk.shared::cluster.global.mbarrier::complete_tx::bytes [%0], [%1], %2, [%3];"
               ::"r"(dst), "l"(src), "r"(bytes), "r"(bar) : "memory");
}
__device__ __forceinline__ void tm_prefetch(const CUtensorMap* tm) {
  asm volatile("prefetch.tensormap [%0];" ::"l"(tm) : "memory");
}

__device__ __forceinline__ void wg_fence() { asm volatile("wgmma.fence.sync.aligned;" ::: "memory"); }
__device__ __forceinline__ void wg_commit() { asm volatile("wgmma.commit_group.sync.aligned;" ::: "memory"); }
template <int N> __device__ __forceinline__ void wg_wait() { asm volatile("wgmma.wait_group.sync.aligned %0;" ::"n"(N) : "memory"); }
__device__ __forceinline__ uint32_t desc_lo(uint32_t addr, uint32_t lbo) { return ((addr & 0x3FFFF) >> 4) | ((lbo >> 4) << 16); }
constexpr uint32_t desc_hi(uint32_t sbo, uint32_t swz) { return (sbo >> 4) | (swz << 30); }
constexpr uint32_t HI_SW128 = desc_hi(1024, 1), HI_SW64 = desc_hi(512, 2), HI_SW32 = desc_hi(256, 3), HI_NONE = desc_hi(128, 0);
template <int N> __device__ __forceinline__ void pin(float* d) {
#pragma unroll
  for (int i = 0; i < N; i++) asm volatile("" : "+f"(d[i])::"memory");
}

__device__ __forceinline__ uint32_t lds32(uint32_t a) {
  uint32_t v;
  asm volatile("ld.volatile.shared.u32 %0, [%1];" : "=r"(v) : "r"(a) : "memory");
  return v;
}
__device__ __forceinline__ uint4 ldg128(const void* a) {
  uint4 v;
  asm volatile("ld.global.nc.v4.u32 {%0, %1, %2, %3}, [%4];" : "=r"(v.x), "=r"(v.y), "=r"(v.z), "=r"(v.w) : "l"(a) : "memory");
  return v;
}
__device__ __forceinline__ uint2 ldg64(const void* a) {
  uint2 v;
  asm volatile("ld.global.nc.v2.u32 {%0, %1}, [%2];" : "=r"(v.x), "=r"(v.y) : "l"(a) : "memory");
  return v;
}
__device__ __forceinline__ void ldsm4(uint32_t* r, uint32_t a) {
  asm volatile("ldmatrix.sync.aligned.m8n8.x4.shared.b16 {%0, %1, %2, %3}, [%4];"
               : "=r"(r[0]), "=r"(r[1]), "=r"(r[2]), "=r"(r[3]) : "r"(a) : "memory");
}
__device__ __forceinline__ void ldsm4t(uint32_t* r, uint32_t a) {
  asm volatile("ldmatrix.sync.aligned.m8n8.x4.trans.shared.b16 {%0, %1, %2, %3}, [%4];"
               : "=r"(r[0]), "=r"(r[1]), "=r"(r[2]), "=r"(r[3]) : "r"(a) : "memory");
}
__device__ __forceinline__ uint2 lds64(uint32_t a) {
  uint2 v;
  asm volatile("ld.shared.v2.u32 {%0, %1}, [%2];" : "=r"(v.x), "=r"(v.y) : "r"(a) : "memory");
  return v;
}
__device__ __forceinline__ uint4 lds128(uint32_t a) {
  uint4 v;
  asm volatile("ld.shared.v4.u32 {%0, %1, %2, %3}, [%4];" : "=r"(v.x), "=r"(v.y), "=r"(v.z), "=r"(v.w) : "r"(a) : "memory");
  return v;
}
__device__ __forceinline__ void sts128(uint32_t a, uint32_t x, uint32_t y, uint32_t z, uint32_t w) {
  asm volatile("st.shared.v4.u32 [%0], {%1, %2, %3, %4};" ::"r"(a), "r"(x), "r"(y), "r"(z), "r"(w) : "memory");
}
__device__ __forceinline__ void stsm4(uint32_t a, const uint32_t* r) {
  asm volatile("stmatrix.sync.aligned.m8n8.x4.shared.b16 [%0], {%1, %2, %3, %4};" ::"r"(a), "r"(r[0]), "r"(r[1]), "r"(r[2]), "r"(r[3]) : "memory");
}
__device__ __forceinline__ void stsm4t(uint32_t a, const uint32_t* r) {
  asm volatile("stmatrix.sync.aligned.m8n8.x4.trans.shared.b16 [%0], {%1, %2, %3, %4};" ::"r"(a), "r"(r[0]), "r"(r[1]), "r"(r[2]), "r"(r[3]) : "memory");
}
__device__ __forceinline__ uint32_t pack2(float lo, float hi) {
  uint32_t r;
  asm("cvt.rn.bf16x2.f32 %0, %1, %2;" : "=r"(r) : "f"(hi), "f"(lo));
  return r;
}
__device__ __forceinline__ uint32_t movm(uint32_t a) {
  uint32_t d;
  asm volatile("movmatrix.sync.aligned.m8n8.trans.b16 %0, %1;" : "=r"(d) : "r"(a));
  return d;
}
__device__ __forceinline__ uint32_t bmul(uint32_t a, uint32_t b) {
  uint32_t d;
  asm("mul.rn.bf16x2 %0, %1, %2;" : "=r"(d) : "r"(a), "r"(b));
  return d;
}
__device__ __forceinline__ uint32_t badd(uint32_t a, uint32_t b) {
  uint32_t d;
  asm("add.rn.bf16x2 %0, %1, %2;" : "=r"(d) : "r"(a), "r"(b));
  return d;
}
__device__ __forceinline__ uint32_t bfma(uint32_t a, uint32_t b, uint32_t c) {
  uint32_t d;
  asm("fma.rn.bf16x2 %0, %1, %2, %3;" : "=r"(d) : "r"(a), "r"(b), "r"(c));
  return d;
}
__device__ __forceinline__ float bf_lo(uint32_t x) { return __uint_as_float(x << 16); }
__device__ __forceinline__ float bf_hi(uint32_t x) { return __uint_as_float(x & 0xFFFF0000u); }
__device__ __forceinline__ float ex2(float x) {
  float y;
  asm("ex2.approx.ftz.f32 %0, %1;" : "=f"(y) : "f"(x));
  return y;
}
__device__ __forceinline__ float rcp(float x) {
  float y;
  asm("rcp.approx.ftz.f32 %0, %1;" : "=f"(y) : "f"(x));
  return y;
}
__device__ __forceinline__ void mma16816(float* d, uint32_t a0, uint32_t a1, uint32_t a2, uint32_t a3, uint32_t b0, uint32_t b1) {
  asm volatile("mma.sync.aligned.m16n8k16.row.col.f32.bf16.bf16.f32 {%0, %1, %2, %3}, {%4, %5, %6, %7}, {%8, %9}, {%0, %1, %2, %3};"
               : "+f"(d[0]), "+f"(d[1]), "+f"(d[2]), "+f"(d[3])
               : "r"(a0), "r"(a1), "r"(a2), "r"(a3), "r"(b0), "r"(b1));
}
__device__ __forceinline__ void mma1688(float* d, uint32_t a0, uint32_t a1, uint32_t b0) {
  asm volatile("mma.sync.aligned.m16n8k8.row.col.f32.bf16.bf16.f32 {%0, %1, %2, %3}, {%4, %5}, {%6}, {%0, %1, %2, %3};"
               : "+f"(d[0]), "+f"(d[1]), "+f"(d[2]), "+f"(d[3])
               : "r"(a0), "r"(a1), "r"(b0));
}

template <int N> struct WgRS;
template <int N> struct WgSST;
template <> struct WgRS<32> {
  template <uint32_t HB>
  static __device__ __forceinline__ void mma(float* d, const uint32_t* a, uint32_t db) {
    asm volatile("{\n.reg .pred p;\n.reg .b64 db;\nsetp.ne.b32 p, %22, 0;\n"
      "mov.b64 db, {%20, %21};\n"
      "wgmma.mma_async.sync.aligned.m64n32k16.f32.bf16.bf16 {"
      "%0, %1, %2, %3, %4, %5, %6, %7, %8, %9, %10, %11, %12, %13, %14, %15"
      "}, {%16, %17, %18, %19}, db, p, 1, 1, 1;\n}\n"
      : "+f"(d[0]), "+f"(d[1]), "+f"(d[2]), "+f"(d[3]), "+f"(d[4]), "+f"(d[5]), "+f"(d[6]), "+f"(d[7]),
        "+f"(d[8]), "+f"(d[9]), "+f"(d[10]), "+f"(d[11]), "+f"(d[12]), "+f"(d[13]), "+f"(d[14]), "+f"(d[15])
      : "r"(a[0]), "r"(a[1]), "r"(a[2]), "r"(a[3]), "r"(db), "n"(HB), "n"(1));
  }
  template <uint32_t HB>
  static __device__ __forceinline__ void set(float* d, const uint32_t* a, uint32_t db) {
    asm volatile("{\n.reg .pred p;\n.reg .b64 db;\nsetp.ne.b32 p, %22, 0;\n"
      "mov.b64 db, {%20, %21};\n"
      "wgmma.mma_async.sync.aligned.m64n32k16.f32.bf16.bf16 {"
      "%0, %1, %2, %3, %4, %5, %6, %7, %8, %9, %10, %11, %12, %13, %14, %15"
      "}, {%16, %17, %18, %19}, db, p, 1, 1, 1;\n}\n"
      : "=f"(d[0]), "=f"(d[1]), "=f"(d[2]), "=f"(d[3]), "=f"(d[4]), "=f"(d[5]), "=f"(d[6]), "=f"(d[7]),
        "=f"(d[8]), "=f"(d[9]), "=f"(d[10]), "=f"(d[11]), "=f"(d[12]), "=f"(d[13]), "=f"(d[14]), "=f"(d[15])
      : "r"(a[0]), "r"(a[1]), "r"(a[2]), "r"(a[3]), "r"(db), "n"(HB), "n"(0));
  }
};
template <> struct WgRS<64> {
  template <uint32_t HB>
  static __device__ __forceinline__ void mma(float* d, const uint32_t* a, uint32_t db) {
    asm volatile("{\n.reg .pred p;\n.reg .b64 db;\nsetp.ne.b32 p, %38, 0;\n"
      "mov.b64 db, {%36, %37};\n"
      "wgmma.mma_async.sync.aligned.m64n64k16.f32.bf16.bf16 {"
      "%0, %1, %2, %3, %4, %5, %6, %7, %8, %9, %10, %11, %12, %13, %14, %15, "
      "%16, %17, %18, %19, %20, %21, %22, %23, %24, %25, %26, %27, %28, %29, %30, %31"
      "}, {%32, %33, %34, %35}, db, p, 1, 1, 1;\n}\n"
      : "+f"(d[0]), "+f"(d[1]), "+f"(d[2]), "+f"(d[3]), "+f"(d[4]), "+f"(d[5]), "+f"(d[6]), "+f"(d[7]),
        "+f"(d[8]), "+f"(d[9]), "+f"(d[10]), "+f"(d[11]), "+f"(d[12]), "+f"(d[13]), "+f"(d[14]), "+f"(d[15]),
        "+f"(d[16]), "+f"(d[17]), "+f"(d[18]), "+f"(d[19]), "+f"(d[20]), "+f"(d[21]), "+f"(d[22]), "+f"(d[23]),
        "+f"(d[24]), "+f"(d[25]), "+f"(d[26]), "+f"(d[27]), "+f"(d[28]), "+f"(d[29]), "+f"(d[30]), "+f"(d[31])
      : "r"(a[0]), "r"(a[1]), "r"(a[2]), "r"(a[3]), "r"(db), "n"(HB), "n"(1));
  }
  template <uint32_t HB>
  static __device__ __forceinline__ void set(float* d, const uint32_t* a, uint32_t db) {
    asm volatile("{\n.reg .pred p;\n.reg .b64 db;\nsetp.ne.b32 p, %38, 0;\n"
      "mov.b64 db, {%36, %37};\n"
      "wgmma.mma_async.sync.aligned.m64n64k16.f32.bf16.bf16 {"
      "%0, %1, %2, %3, %4, %5, %6, %7, %8, %9, %10, %11, %12, %13, %14, %15, "
      "%16, %17, %18, %19, %20, %21, %22, %23, %24, %25, %26, %27, %28, %29, %30, %31"
      "}, {%32, %33, %34, %35}, db, p, 1, 1, 1;\n}\n"
      : "=f"(d[0]), "=f"(d[1]), "=f"(d[2]), "=f"(d[3]), "=f"(d[4]), "=f"(d[5]), "=f"(d[6]), "=f"(d[7]),
        "=f"(d[8]), "=f"(d[9]), "=f"(d[10]), "=f"(d[11]), "=f"(d[12]), "=f"(d[13]), "=f"(d[14]), "=f"(d[15]),
        "=f"(d[16]), "=f"(d[17]), "=f"(d[18]), "=f"(d[19]), "=f"(d[20]), "=f"(d[21]), "=f"(d[22]), "=f"(d[23]),
        "=f"(d[24]), "=f"(d[25]), "=f"(d[26]), "=f"(d[27]), "=f"(d[28]), "=f"(d[29]), "=f"(d[30]), "=f"(d[31])
      : "r"(a[0]), "r"(a[1]), "r"(a[2]), "r"(a[3]), "r"(db), "n"(HB), "n"(0));
  }
};
template <> struct WgSST<48> {
  template <uint32_t HA, uint32_t HB>
  static __device__ __forceinline__ void mma(float* d, uint32_t da, uint32_t db, int sc) {
    asm volatile("{\n.reg .pred p;\n.reg .b64 da, db;\nsetp.ne.b32 p, %28, 0;\n"
      "mov.b64 da, {%24, %25};\nmov.b64 db, {%26, %27};\n"
      "wgmma.mma_async.sync.aligned.m64n48k16.f32.bf16.bf16 {"
      "%0, %1, %2, %3, %4, %5, %6, %7, %8, %9, %10, %11, %12, %13, %14, %15, "
      "%16, %17, %18, %19, %20, %21, %22, %23"
      "}, da, db, p, 1, 1, 0, 1;\n}\n"
      : "+f"(d[0]), "+f"(d[1]), "+f"(d[2]), "+f"(d[3]), "+f"(d[4]), "+f"(d[5]), "+f"(d[6]), "+f"(d[7]),
        "+f"(d[8]), "+f"(d[9]), "+f"(d[10]), "+f"(d[11]), "+f"(d[12]), "+f"(d[13]), "+f"(d[14]), "+f"(d[15]),
        "+f"(d[16]), "+f"(d[17]), "+f"(d[18]), "+f"(d[19]), "+f"(d[20]), "+f"(d[21]), "+f"(d[22]), "+f"(d[23])
      : "r"(da), "n"(HA), "r"(db), "n"(HB), "r"(sc));
  }
};
template <> struct WgSST<80> {
  template <uint32_t HA, uint32_t HB>
  static __device__ __forceinline__ void mma(float* d, uint32_t da, uint32_t db, int sc) {
    asm volatile("{\n.reg .pred p;\n.reg .b64 da, db;\nsetp.ne.b32 p, %44, 0;\n"
      "mov.b64 da, {%40, %41};\nmov.b64 db, {%42, %43};\n"
      "wgmma.mma_async.sync.aligned.m64n80k16.f32.bf16.bf16 {"
      "%0, %1, %2, %3, %4, %5, %6, %7, %8, %9, %10, %11, %12, %13, %14, %15, "
      "%16, %17, %18, %19, %20, %21, %22, %23, %24, %25, %26, %27, %28, %29, %30, %31, "
      "%32, %33, %34, %35, %36, %37, %38, %39"
      "}, da, db, p, 1, 1, 0, 1;\n}\n"
      : "+f"(d[0]), "+f"(d[1]), "+f"(d[2]), "+f"(d[3]), "+f"(d[4]), "+f"(d[5]), "+f"(d[6]), "+f"(d[7]),
        "+f"(d[8]), "+f"(d[9]), "+f"(d[10]), "+f"(d[11]), "+f"(d[12]), "+f"(d[13]), "+f"(d[14]), "+f"(d[15]),
        "+f"(d[16]), "+f"(d[17]), "+f"(d[18]), "+f"(d[19]), "+f"(d[20]), "+f"(d[21]), "+f"(d[22]), "+f"(d[23]),
        "+f"(d[24]), "+f"(d[25]), "+f"(d[26]), "+f"(d[27]), "+f"(d[28]), "+f"(d[29]), "+f"(d[30]), "+f"(d[31]),
        "+f"(d[32]), "+f"(d[33]), "+f"(d[34]), "+f"(d[35]), "+f"(d[36]), "+f"(d[37]), "+f"(d[38]), "+f"(d[39])
      : "r"(da), "n"(HA), "r"(db), "n"(HB), "r"(sc));
  }
};
template <> struct WgSST<192> {
  template <uint32_t HA, uint32_t HB>
  static __device__ __forceinline__ void mma(float* d, uint32_t da, uint32_t db, int sc) {
    asm volatile("{\n.reg .pred p;\n.reg .b64 da, db;\nsetp.ne.b32 p, %100, 0;\n"
      "mov.b64 da, {%96, %97};\nmov.b64 db, {%98, %99};\n"
      "wgmma.mma_async.sync.aligned.m64n192k16.f32.bf16.bf16 {"
      "%0, %1, %2, %3, %4, %5, %6, %7, %8, %9, %10, %11, %12, %13, %14, %15, "
      "%16, %17, %18, %19, %20, %21, %22, %23, %24, %25, %26, %27, %28, %29, %30, %31, "
      "%32, %33, %34, %35, %36, %37, %38, %39, %40, %41, %42, %43, %44, %45, %46, %47, "
      "%48, %49, %50, %51, %52, %53, %54, %55, %56, %57, %58, %59, %60, %61, %62, %63, "
      "%64, %65, %66, %67, %68, %69, %70, %71, %72, %73, %74, %75, %76, %77, %78, %79, "
      "%80, %81, %82, %83, %84, %85, %86, %87, %88, %89, %90, %91, %92, %93, %94, %95"
      "}, da, db, p, 1, 1, 0, 1;\n}\n"
      : "+f"(d[0]), "+f"(d[1]), "+f"(d[2]), "+f"(d[3]), "+f"(d[4]), "+f"(d[5]), "+f"(d[6]), "+f"(d[7]),
        "+f"(d[8]), "+f"(d[9]), "+f"(d[10]), "+f"(d[11]), "+f"(d[12]), "+f"(d[13]), "+f"(d[14]), "+f"(d[15]),
        "+f"(d[16]), "+f"(d[17]), "+f"(d[18]), "+f"(d[19]), "+f"(d[20]), "+f"(d[21]), "+f"(d[22]), "+f"(d[23]),
        "+f"(d[24]), "+f"(d[25]), "+f"(d[26]), "+f"(d[27]), "+f"(d[28]), "+f"(d[29]), "+f"(d[30]), "+f"(d[31]),
        "+f"(d[32]), "+f"(d[33]), "+f"(d[34]), "+f"(d[35]), "+f"(d[36]), "+f"(d[37]), "+f"(d[38]), "+f"(d[39]),
        "+f"(d[40]), "+f"(d[41]), "+f"(d[42]), "+f"(d[43]), "+f"(d[44]), "+f"(d[45]), "+f"(d[46]), "+f"(d[47]),
        "+f"(d[48]), "+f"(d[49]), "+f"(d[50]), "+f"(d[51]), "+f"(d[52]), "+f"(d[53]), "+f"(d[54]), "+f"(d[55]),
        "+f"(d[56]), "+f"(d[57]), "+f"(d[58]), "+f"(d[59]), "+f"(d[60]), "+f"(d[61]), "+f"(d[62]), "+f"(d[63]),
        "+f"(d[64]), "+f"(d[65]), "+f"(d[66]), "+f"(d[67]), "+f"(d[68]), "+f"(d[69]), "+f"(d[70]), "+f"(d[71]),
        "+f"(d[72]), "+f"(d[73]), "+f"(d[74]), "+f"(d[75]), "+f"(d[76]), "+f"(d[77]), "+f"(d[78]), "+f"(d[79]),
        "+f"(d[80]), "+f"(d[81]), "+f"(d[82]), "+f"(d[83]), "+f"(d[84]), "+f"(d[85]), "+f"(d[86]), "+f"(d[87]),
        "+f"(d[88]), "+f"(d[89]), "+f"(d[90]), "+f"(d[91]), "+f"(d[92]), "+f"(d[93]), "+f"(d[94]), "+f"(d[95])
      : "r"(da), "n"(HA), "r"(db), "n"(HB), "r"(sc));
  }
};

struct FftConst {
  uint32_t f[2][4], fi[4][4];
  uint32_t ta[2][2], tb[2][2];
};
__device__ __forceinline__ void cis(int m, float scale, float& c, float& s) {
  const float a = (float)m * (-6.283185307179586f * scale);
  c = __cosf(a);
  s = __sinf(a);
}
__device__ __forceinline__ void fft_tables(uint32_t (&v)[12], int tw) {
  const int row = tw >> 2, ch = tw & 3;
#pragma unroll
  for (int i = 0; i < 4; i++) {
    float c[2], s[2], x[2];
#pragma unroll
    for (int e = 0; e < 2; e++) {
      cis((((32 * (8 * ch + 2 * i + e) + 15) * (4 * row - 63) + 2048) & 4095) - 2048, 1.f / 4096, c[e], s[e]);
      float gc, gs;
      cis((((row & 15) * (8 * (ch & 1) + 2 * i + e) + 8) & 15) - 8, 1.f / 16, gc, gs);
      x[e] = (row >> 4) == (ch >> 1) ? gc : (ch >> 1) ? gs : -gs;
    }
    v[i] = pack2(c[0] * 0.125f, c[1] * 0.125f);
    v[4 + i] = pack2(s[0] * 0.125f, s[1] * 0.125f);
    v[8 + i] = pack2(x[0], x[1]);
  }
#pragma unroll
  for (int i = 0; i < 12; i++) asm volatile("" : "+r"(v[i]));
}
__device__ __forceinline__ void fft_tables_store(const uint32_t (&v)[12], uint32_t sb, int tw) {
  const int row = tw >> 2;
  const uint32_t x = ((tw ^ (row >> 1)) & 3) << 4, a = sb + OFF_FT + (16 * (row >> 3) + (row & 7)) * 64 + x;
  sts128(a, v[0], v[1], v[2], v[3]);
  sts128(a + 512, v[4], v[5], v[6], v[7]);
  sts128(sb + OFF_GT + row * 64 + x, v[8], v[9], v[10], v[11]);
}
__device__ __forceinline__ void fft_twiddles(uint32_t (&v)[2], int tw) {
  float a[2], s[2];
#pragma unroll
  for (int i = 0; i < 2; i++) {
    float c;
    cis((2 * (2 * (tw & 3) + i) - 15) * (4 * (tw >> 2) - 63), 1.f / 4096, c, s[i]);
    a[i] = __fdividef(-s[i], 1.f + c);
  }
  v[0] = pack2(a[0], a[1]);
  v[1] = pack2(s[0], s[1]);
  asm volatile("" : "+r"(v[0]), "+r"(v[1]));
}
__device__ __forceinline__ void fft_matrices(FftConst& k, uint32_t sb, int w, int lane) {
  const uint32_t x = (lane >> 1) & 3;
  const uint2 t0 = lds64(sb + OFF_TT + 256 * w + 8 * lane), t1 = lds64(sb + OFF_TT + 256 * w + 8 * (lane ^ 3));
  k.ta[0][0] = t0.x;
  k.tb[0][0] = t0.y;
  k.ta[1][1] = __byte_perm(t1.x, 0, 0x1032);
  k.tb[1][1] = __byte_perm(t1.y, 0, 0x1032);
#pragma unroll
  for (int j = 0; j < 2; j++) {
    k.ta[1 - j][j] = k.ta[j][j] ^ 0x80008000u;
    k.tb[1 - j][j] = k.tb[j][j] ^ 0x80008000u;
    asm volatile("" : "+r"(k.ta[0][j]), "+r"(k.tb[0][j]), "+r"(k.ta[1][j]), "+r"(k.tb[1][j]));
  }
#pragma unroll
  for (int i = 0; i < 2; i++) {
    ldsm4(k.f[i], sb + OFF_FT + (16 * w + (lane & 15)) * 64 + (((2 * i + (lane >> 4)) ^ x) << 4));
    ldsm4t(k.fi[i], sb + OFF_FT + (32 * i + lane) * 64 + ((w ^ x) << 4));
#pragma unroll
    for (int j = 0; j < 4; j++) {
      k.fi[2 + i][j] = (j & 1) ? k.fi[i][j - 1] ^ 0x80008000u : k.fi[i][j + 1];
      asm volatile("" : "+r"(k.fi[2 + i][j]));
    }
  }
}
__device__ __forceinline__ void rot(uint32_t& x, uint32_t& y, uint32_t a, uint32_t b) {
  x = bfma(a, y, x);
  y = bfma(b, x, y);
  x = bfma(a, y, x);
}
__device__ __forceinline__ void twiddle_fwd(uint32_t (&a)[4][4], float* d, const FftConst& k) {
#pragma unroll
  for (int q = 0; q < 4; q++)
#pragma unroll
    for (int j = 0; j < 2; j++) {
      const float* x = d + 8 * q + 4 * j;
      uint32_t re = pack2(x[0], x[1]), im = pack2(x[2], x[3]);
      rot(re, im, k.ta[0][j], k.tb[0][j]);
      a[q & 2][2 * j + (q & 1)] = re;
      a[(q & 2) + 1][2 * j + (q & 1)] = im;
    }
}
__device__ __forceinline__ void g_step(float* d, const uint32_t (&a)[4][4], uint32_t dre, uint32_t dim) {
  WgRS<32>::set<HI_SW64>(d, a[0], dre);
  WgRS<32>::set<HI_SW64>(d + 16, a[2], dre);
  WgRS<32>::mma<HI_SW64>(d, a[1], dim);
  WgRS<32>::mma<HI_SW64>(d + 16, a[3], dim);
  wg_commit();
}

__device__ __forceinline__ void conv_channel(const FftConst& k, uint32_t sb, int c, int wg, int w, int lane) {
  const uint32_t cb = sb + off_ch(c), bars = sb + OFF_BAR;
  const uint32_t du = desc_lo(cb, 1024), dg = desc_lo(sb + OFF_GT, 16), dz = desc_lo(cb + U_BYTES, 16);
  float U[32], H[32];
  uint32_t a[4][4], e[4][4];
  const float dv = __uint_as_float(lds32(sb + OFF_D + 4 * c));
  wg_fence();
  WgRS<64>::set<HI_SW32>(H, k.f[0], du + 256);
  WgRS<64>::mma<HI_SW32>(H, k.f[1], du + 256 + 32);
  wg_commit();
  wg_wait<0>();
  pin<32>(H);
  twiddle_fwd(a, H, k);
  if (ATT_GATE) mbar_wait(bars + 8 * (ATT_GATE == 1 ? B_ATTN : B_ATT2), 0);
  mbar_wait(bars + 8 * (B_U + (c < 3 ? c : 3)), 0);
  TSM(w == 0 && c < 3, 7 + wg);
  wg_fence();
  WgRS<64>::set<HI_SW32>(U, k.f[0], du);
  WgRS<64>::mma<HI_SW32>(U, k.f[1], du + 32);
  wg_commit();
  g_step(H, a, dg, dg + 64);
  wg_wait<1>();
  pin<32>(U);
  twiddle_fwd(e, U, k);
  wg_fence();
  g_step(U, e, dg, dg + 64);
  wg_wait<0>();
  pin<32>(U);
  pin<32>(H);
#pragma unroll
  for (int j = 0; j < 2; j++) {
    float pr[4][2], pi[4][2];
#pragma unroll
    for (int x = 0; x < 2; x++) {
      H[4 * j + x] += dv;
#pragma unroll
      for (int m = 0; m < 4; m++) {
#pragma unroll
        for (int q = 0; q <= m; q++) {
          const int ih = 16 * (q >> 1) + 2 * (q & 1) + 4 * j + x, iu = 16 * ((m - q) >> 1) + 2 * ((m - q) & 1) + 4 * j + x;
          pr[m][x] = q ? fmaf(H[ih], U[iu], pr[m][x]) : H[ih] * U[iu];
          pi[m][x] = q ? fmaf(H[ih], U[iu + 8], pi[m][x]) : H[ih] * U[iu + 8];
          pr[m][x] = fmaf(-H[ih + 8], U[iu + 8], pr[m][x]);
          pi[m][x] = fmaf(H[ih + 8], U[iu], pi[m][x]);
        }
      }
    }
#pragma unroll
    for (int m = 0; m < 4; m++) {
      a[m & 2][2 * j + (m & 1)] = pack2(pr[m][0], pr[m][1]);
      a[(m & 2) + 1][2 * j + (m & 1)] = pack2(pi[m][0], pi[m][1]);
    }
  }
  wg_fence();
  g_step(U, a, dg + 64, dg);
  const uint32_t za = cb + U_BYTES + (8 * w + (lane & 7)) * 128 + (((lane >> 3) ^ (lane & 7)) << 4);
  const uint32_t ya = cb + (lane >> 4) * 1024 + (8 * w + (lane & 7)) * 32 + ((((lane >> 3) ^ (lane >> 2)) & 1) << 4);
  wg_sync(1 + wg);
  wg_wait<0>();
  pin<32>(U);
  TSIF(w == 0, 80 + c);
#pragma unroll
  for (int p = 0; p < 2; p++) {
#pragma unroll
    for (int i = 0; i < 4; i++) {
      const int j = i & 1;
      const float* x = U + 16 * p + 4 * j + (i & 2);
      e[p][i] = pack2(x[8], x[9]);
      e[2 + p][i] = pack2(x[0], x[1]);
      rot(e[p][i], e[2 + p][i], k.ta[1][j], k.tb[1][j]);
    }
    stsm4(za ^ (64 * p), e[p]);
    stsm4((za ^ (64 * p)) + 4096, e[2 + p]);
  }
  fence_async_smem();
  wg_sync(1 + wg);
  wg_fence();
  WgRS<64>::set<HI_SW128>(H, k.fi[0], dz);
#pragma unroll
  for (int ks = 1; ks < 4; ks++) WgRS<64>::mma<HI_SW128>(H, k.fi[ks], dz + 128 * ks);
  wg_commit();
  if (WO_FAST) mbar_wait(bars + 8 * B_ATTN, 0);
  wg_wait<0>();
  pin<32>(H);
  TSIF(w == 0, 88 + c);
#pragma unroll
  for (int j = 0; j < 8; j++)
    a[j >> 2][j & 3] = j < 2 ? pack2(H[4 * j], H[4 * j + 1]) : pack2(H[4 * j] + H[4 * j - 6], H[4 * j + 1] + H[4 * j - 5]);
  stsm4(ya, a[0]);
  stsm4(ya + 2048, a[1]);
  fence_async_smem();
  __syncwarp();
}

__device__ __forceinline__ void prep_slab(uint4* res, const uint2* sw, uint32_t sb, int slab, int w, int lane) {
  const int t = lane & 3, tp = (lane & 7) >> 1, pos = 8 * tp + 2 * (((lane >> 3) + tp) & 3) + (lane & 1);
  const uint32_t base = sb + OFF_KVS + slab * KVS_BYTES + pos * 128;
  uint32_t kk[2][4][4], vv[2][4];
  mbar_wait(sb + OFF_BAR + 8 * (B_KV + slab), 0);
#pragma unroll
  for (int h = 0; h < 2; h++) {
#pragma unroll
    for (int j = 0; j < 4; j++) {
      const uint32_t a = base + 128 * j;
      ldsm4t(kk[h][j], a + (((w + 4 * h) ^ ((a >> 7) & 7)) << 4));
    }
    const uint32_t a = base + KVS_V;
    ldsm4t(vv[h], a + (((w + 4 * h) ^ ((a >> 7) & 7)) << 4));
  }
#pragma unroll
  for (int h = 0; h < 2; h++) {
    uint32_t (&k)[4][4] = kk[h];
    uint32_t (&v)[4] = vv[h];
    const uint32_t w0 = __byte_perm(sw[h].x, 0, 0x1010), w1 = __byte_perm(sw[h].x, 0, 0x3232);
    const uint32_t w2 = __byte_perm(sw[h].y, 0, 0x1010), w3 = __byte_perm(sw[h].y, 0, 0x3232);
#pragma unroll
    for (int m = 0; m < 4; m++)
      v[m] = bmul(badd(badd(badd(bmul(k[0][m], w3), bmul(k[1][m], w2)), bmul(k[2][m], w1)), bmul(k[3][m], w0)), v[m]);
    uint32_t a[4];
#pragma unroll
    for (int m = 0; m < 4; m++) a[m] = (t & 1) ? v[(m + 3) & 3] : v[m];
    res[h] = (t & 2) ? make_uint4(a[2], a[3], a[0], a[1]) : make_uint4(a[0], a[1], a[2], a[3]);
  }
}

__device__ __forceinline__ void prep_gate(const Params& p, uint32_t sb, int b, int w, int lane) {
  uint2 gw[5], x[4][5];
#pragma unroll
  for (int j = 0; j < 5; j++) gw[j] = ldg64(reinterpret_cast<const uint2*>(p.gate_w) + lane + 32 * j);
#pragma unroll
  for (int i = 0; i < 4; i++)
#pragma unroll
    for (int j = 0; j < 5; j++)
      x[i][j] = ldg64(reinterpret_cast<const uint2*>(p.q) + (16 * b + 4 * w + i) * (DIM / 4) + lane + 32 * j);
  float s[4];
#pragma unroll
  for (int i = 0; i < 4; i++) {
    s[i] = 0.f;
#pragma unroll
    for (int j = 0; j < 5; j++) {
      const uint32_t m0 = bmul(x[i][j].x, gw[j].x), m1 = bmul(x[i][j].y, gw[j].y);
      s[i] += (bf_lo(m0) + bf_hi(m0)) + (bf_lo(m1) + bf_hi(m1));
    }
  }
  const bool h = lane & 16, q = lane & 8;
  const float a = (h ? s[2] : s[0]) + __shfl_xor_sync(0xffffffffu, h ? s[0] : s[2], 16);
  const float c = (h ? s[3] : s[1]) + __shfl_xor_sync(0xffffffffu, h ? s[1] : s[3], 16);
  float z = (q ? c : a) + __shfl_xor_sync(0xffffffffu, q ? a : c, 8);
#pragma unroll
  for (int o = 4; o > 0; o >>= 1) z += __shfl_xor_sync(0xffffffffu, z, o);
  z = bf_lo(pack2(z, 0.f));
  z = bf_lo(pack2(__fdividef(1.f, 1.f + __expf(-z)), 0.f));
  if (G_TMA) {
    mbar_wait(sb + OFF_BAR + 8 * B_S3, 0);
    if ((lane & 7) == 0) asm volatile("st.shared.f32 [%0], %1;" ::"r"(sb + OFF_GATE + 64 * (b & 7) + 16 * w + (lane >> 1)), "f"(z) : "memory");
    fence_async_smem();
  } else if ((lane & 7) == 0) {
    g_gate[16 * b + 4 * w + (lane >> 3)] = z;
  }
}

__device__ __forceinline__ uint32_t bmax(uint32_t a, uint32_t b) {
  uint32_t d;
  asm("max.bf16x2 %0, %1, %2;" : "=r"(d) : "r"(a), "r"(b));
  return d;
}
__device__ __forceinline__ void softmax_two(const float (&l)[2][2], uint32_t& p0, uint32_t& p1) {
  constexpr float kScale = 0.22360679774997896f, kLog2e = 1.4426950408889634f;
  const uint32_t r0 = pack2(l[0][0], l[1][0]), r1 = pack2(l[0][1], l[1][1]);
  const uint32_t x0 = pack2(bf_lo(r0) * kScale, bf_hi(r0) * kScale), x1 = pack2(bf_lo(r1) * kScale, bf_hi(r1) * kScale);
  uint32_t m = bmax(x0, x1);
  m = bmax(m, __shfl_xor_sync(0xffffffffu, m, 1));
  m = bmax(m, __shfl_xor_sync(0xffffffffu, m, 2));
  const float m0 = bf_lo(m) * kLog2e, m1 = bf_hi(m) * kLog2e;
  p0 = pack2(ex2(bf_lo(x0) * kLog2e - m0), ex2(bf_lo(x1) * kLog2e - m0));
  p1 = pack2(ex2(bf_hi(x0) * kLog2e - m1), ex2(bf_hi(x1) * kLog2e - m1));
}

__device__ __forceinline__ void halo_read(uint32_t (&kpv)[10], uint32_t (&vpv)[10], uint32_t (&tg)[7], const uint4* hp) {
#pragma unroll
  for (int j = 0; j < 7; j++) {
    uint32_t x0, x1, x2;
    asm volatile("ld.relaxed.gpu.global.v4.u32 {%0, %1, %2, %3}, [%4];"
                 : "=r"(x0), "=r"(x1), "=r"(x2), "=r"(tg[j]) : "l"(hp + 32 * j) : "memory");
    if (j < 4) kpv[3 * j] = x0; else vpv[3 * j - 10] = x0;
    if (j < 3) kpv[3 * j + 1] = x1; else vpv[3 * j - 9] = x1;
    if (j < 3) kpv[3 * j + 2] = x2; else if (j < 6) vpv[3 * j - 8] = x2;
  }
}

template <int ROT>
__device__ __forceinline__ void pack_qkv(const float* acc, uint32_t (&qlo)[10], uint32_t (&qhi)[10], uint32_t (&klo)[10],
                                         uint32_t (&khi)[10], uint32_t (&vlo)[10], uint32_t (&vhi)[10]) {
#pragma unroll
  for (int j = 0; j < 10; j++) {
    const int x = (j + ROT) % 10, tq = x < 8 ? x : 16 + x, tk = x < 8 ? 8 + x : 18 + x, tv = x < 8 ? 16 + x : 20 + x;
    khi[j] = pack2(acc[4 * tk + 2], acc[4 * tk + 3]);
    vhi[j] = movm(pack2(acc[4 * tv + 2], acc[4 * tv + 3]));
    qlo[j] = pack2(acc[4 * tq], acc[4 * tq + 1]);
    qhi[j] = pack2(acc[4 * tq + 2], acc[4 * tq + 3]);
    klo[j] = pack2(acc[4 * tk], acc[4 * tk + 1]);
    vlo[j] = pack2(acc[4 * tv], acc[4 * tv + 1]);
    asm volatile("" : "+r"(khi[j]), "+r"(qlo[j]), "+r"(qhi[j]), "+r"(klo[j]), "+r"(vlo[j]));
  }
}

template <int ROT> __device__ __forceinline__ void halo_send(const float* acc, uint4* ho, uint32_t tag) {
#pragma unroll
  for (int j = 0; j < 7; j++) {
    uint32_t x[3];
#pragma unroll
    for (int e = 0; e < 3; e++) {
      const int i = 3 * j + e, y = (i % 10 + ROT) % 10, tk = y < 8 ? 8 + y : 18 + y, tv = y < 8 ? 16 + y : 20 + y;
      x[e] = i < 10 ? pack2(acc[4 * tk + 2], acc[4 * tk + 3]) : i < 20 ? movm(pack2(acc[4 * tv + 2], acc[4 * tv + 3])) : 0u;
    }
    asm volatile("st.relaxed.gpu.global.v4.u32 [%0], {%1, %2, %3, %4};" ::"l"(ho + 32 * j), "r"(x[0]), "r"(x[1]), "r"(x[2]), "r"(tag) : "memory");
  }
}

__device__ __forceinline__ void attention(float* acc, uint32_t sb, int b, int par, int w, int lane, uint32_t tag, uint32_t zero) {
  const int g = lane >> 2, t = lane & 3;
  uint32_t klo[10], khi[10], vlo[10], vhi[10], qlo[10], qhi[10], kpv[10], vpv[10];
  if (HALO_FIRST && w == 3 && b < NCTA - 8) {
    uint4* ho = g_halo + (b * 2 + par) * 224 + lane;
    if (tail_first(b & 7)) halo_send<8>(acc, ho, tag);
    else halo_send<0>(acc, ho, tag);
    TSIF(par == 0, 76);
    pin<120>(acc);
  }
  if (tail_first(b & 7)) pack_qkv<8>(acc, qlo, qhi, klo, khi, vlo, vhi);
  else pack_qkv<0>(acc, qlo, qhi, klo, khi, vlo, vhi);
  const uint32_t xa = sb + OFF_KVX + (par * 3) * 2560 + lane * 16;
  if (w < 3) {
    sts128(xa + w * 2560, khi[0], khi[1], khi[2], khi[3]);
    sts128(xa + w * 2560 + 512, khi[4], khi[5], khi[6], khi[7]);
    sts128(xa + w * 2560 + 1024, khi[8], khi[9], vhi[0], vhi[1]);
    sts128(xa + w * 2560 + 1536, vhi[2], vhi[3], vhi[4], vhi[5]);
    sts128(xa + w * 2560 + 2048, vhi[6], vhi[7], vhi[8], vhi[9]);
  } else if (!HALO_FIRST && b < NCTA - 8) {
    uint4* ho = g_halo + (b * 2 + par) * 224 + lane;
#pragma unroll
    for (int j = 0; j < 7; j++) {
      const uint32_t x0 = j < 4 ? khi[3 * j] : vhi[3 * j - 10], x1 = j < 3 ? khi[3 * j + 1] : vhi[3 * j - 9];
      const uint32_t x2 = j < 3 ? khi[3 * j + 2] : j < 6 ? vhi[3 * j - 8] : 0u;
      asm volatile("st.relaxed.gpu.global.v4.u32 [%0], {%1, %2, %3, %4};" ::"l"(ho + 32 * j), "r"(x0), "r"(x1), "r"(x2), "r"(tag) : "memory");
    }
  }
  TSIF(par == 0 && w == 1, 64);
  TSIF(par == 0 && w == 3 && !HALO_FIRST, 76);
#pragma unroll
  for (int j = 0; j < 10; j++) vlo[j] = movm(vlo[j]);
  const bool far0 = 2 * t > g, far1 = 2 * t + 1 > g;
  const uint32_t mfar = (far0 ? 0x0000FFFFu : 0u) | (far1 ? 0xFFFF0000u : 0u);
  float slo[4][2], shi[4][2], lg[2][2];
  uint32_t phi[4], plo[4], qml[4], qmh[4];
#pragma unroll
  for (int h = 0; h < 4; h++) {
    const int f = h == 0 ? 0 : h == 1 ? 3 : h == 2 ? 5 : 8, hf = h < 2 ? 2 : 7;
    const bool mine = (h & 1) ? t >= 2 : t < 2;
    qml[h] = mine ? qlo[hf] : 0u;
    qmh[h] = mine ? qhi[hf] : 0u;
    float a[4] = {0.f, 0.f, 0.f, 0.f}, c[4] = {0.f, 0.f, 0.f, 0.f};
    mma16816(a, qlo[f], qhi[f], qlo[f + 1], qhi[f + 1], klo[f], klo[f + 1]);
    mma16816(c, qlo[f], qhi[f], qlo[f + 1], qhi[f + 1], khi[f], khi[f + 1]);
    mma1688(a, qml[h], qmh[h], klo[hf]);
    mma1688(c, qml[h], qmh[h], khi[hf]);
    slo[h][0] = a[0];
    slo[h][1] = a[1];
    shi[h][0] = lg[h & 1][0] = far0 ? a[2] : c[2];
    shi[h][1] = lg[h & 1][1] = far1 ? a[3] : c[3];
    if (!ATT_MERGE && (h & 1)) softmax_two(lg, phi[h - 1], phi[h]);
  }
  TSIF(par == 0 && w == 1, 65);
  if (ATT_GATE == 3 && lane == 0) mbar_arrive(sb + OFF_BAR + 8 * B_ATT2 + (phi[3] & zero));
  wg_sync(1 + par);
  TSIF(par == 0 && w == 1, 66);
  const bool nohist = (w == 0) && (b < 8);
  const uint4* hp = g_halo + ((b - 8) * 2 + par) * 224 + lane;
  uint32_t tg[7];
  if (w > 0) {
    const uint4 v0 = lds128(xa + (w - 1) * 2560), v1 = lds128(xa + (w - 1) * 2560 + 512), v2 = lds128(xa + (w - 1) * 2560 + 1024);
    const uint4 v3 = lds128(xa + (w - 1) * 2560 + 1536), v4 = lds128(xa + (w - 1) * 2560 + 2048);
    kpv[0] = v0.x; kpv[1] = v0.y; kpv[2] = v0.z; kpv[3] = v0.w; kpv[4] = v1.x; kpv[5] = v1.y; kpv[6] = v1.z; kpv[7] = v1.w;
    kpv[8] = v2.x; kpv[9] = v2.y; vpv[0] = v2.z; vpv[1] = v2.w; vpv[2] = v3.x; vpv[3] = v3.y; vpv[4] = v3.z; vpv[5] = v3.w;
    vpv[6] = v4.x; vpv[7] = v4.y; vpv[8] = v4.z; vpv[9] = v4.w;
  } else if (nohist) {
#pragma unroll
    for (int j = 0; j < 10; j++) kpv[j] = vpv[j] = 0u;
  } else {
    TSIF(par == 0, 77);
    halo_read(kpv, vpv, tg, hp);
  }
  if (w == 0 && !nohist) {
    int spins = 0;
    while (true) {
      bool ok = true;
#pragma unroll
      for (int j = 0; j < 7; j++) ok = ok && tg[j] == tag;
      if (__all_sync(0xffffffffu, ok) || ++spins > SPIN_LIMIT) break;
      halo_read(kpv, vpv, tg, hp);
    }
    TSIF(par == 0, 79);
  }
#pragma unroll
  for (int h = 0; h < 4; h++) {
    const int f = h == 0 ? 0 : h == 1 ? 3 : h == 2 ? 5 : 8, hf = h < 2 ? 2 : 7;
    float a[4] = {0.f, 0.f, 0.f, 0.f};
    mma16816(a, qlo[f], qhi[f], qlo[f + 1], qhi[f + 1], kpv[f], kpv[f + 1]);
    mma1688(a, qml[h], qmh[h], kpv[hf]);
    const float ninf = __int_as_float(0xff800000);
    lg[h & 1][0] = far0 ? (nohist ? ninf : a[0]) : slo[h][0];
    lg[h & 1][1] = far1 ? (nohist ? ninf : a[1]) : slo[h][1];
    if (h & 1) {
      softmax_two(lg, plo[h - 1], plo[h]);
      if (ATT_MERGE) {
        const float lh[2][2] = {{shi[h - 1][0], shi[h - 1][1]}, {shi[h][0], shi[h][1]}};
        softmax_two(lh, phi[h - 1], phi[h]);
      }
    }
  }
  TSIF(par == 0 && w <= 1, 67 + w);
  if (ATT_GATE == 2 && lane == 0) mbar_arrive(sb + OFF_BAR + 8 * B_ATT2 + (plo[3] & zero));
  uint32_t ov[20];
#pragma unroll
  for (int hp = 0; hp < 2; hp++) {
    const int hf = hp ? 7 : 2;
    float sh[4] = {0.f, 0.f, 0.f, 0.f}, i0 = 0.f, i1 = 0.f;
#pragma unroll
    for (int e = 0; e < 2; e++) {
      const int h = 2 * hp + e, f = h == 0 ? 0 : h == 1 ? 3 : h == 2 ? 5 : 8;
      const uint32_t a0 = plo[h] & mfar, a2 = plo[h] & ~mfar, a3 = phi[h] & mfar, c1 = phi[h] & ~mfar;
      float sum[4] = {0.f, 0.f, 0.f, 0.f};
      mma1688(sum, plo[h], phi[h], 0x3F803F80u);
      const float r0 = rcp(sum[0]), r1 = rcp(sum[2]);
#pragma unroll
      for (int j = f; j < f + 2; j++) {
        float o[4] = {0.f, 0.f, 0.f, 0.f};
        mma16816(o, a0, 0u, a2, a3, vpv[j], vlo[j]);
        mma1688(o, 0u, c1, vhi[j]);
        ov[2 * j] = pack2(o[0] * r0, o[1] * r0);
        ov[2 * j + 1] = pack2(o[2] * r1, o[3] * r1);
      }
      const bool mine = e ? g >= 4 : g < 4;
      mma16816(sh, a0, 0u, a2, a3, mine ? vpv[hf] : 0u, mine ? vlo[hf] : 0u);
      mma1688(sh, 0u, c1, mine ? vhi[hf] : 0u);
      if (e == 0 || t >= 2) {
        i0 = r0;
        i1 = r1;
      }
    }
    ov[2 * hf] = pack2(sh[0] * i0, sh[1] * i0);
    ov[2 * hf + 1] = pack2(sh[2] * i1, sh[3] * i1);
  }
  if (ATT_GATE == 4 && lane == 0) mbar_arrive(sb + OFF_BAR + 8 * B_ATT2 + (ov[19] & zero));
  TS(32 + 4 * par + w);
  mbar_wait(sb + OFF_BAR + 8 * B_P1, 0);
  const uint32_t oa = sb + OFF_OA + (lane >> 4) * 2048 + (32 * w + 2 * (lane & 15) + par) * 16;
#pragma unroll
  for (int j = 0; j < 5; j++) stsm4(oa + 4096 * j, ov + 4 * j);
  TSIF(par == 0 && w == 0, 120);
  fence_async_smem();
  TSIF(par == 0 && w == 0, 121);
  __syncwarp();
  if (lane == 0) mbar_arrive(sb + OFF_BAR + 8 * B_ATTN);
  TSM(w == 0 || w == 2, 122 + par + (w == 2 ? 3 : 0));
}

struct Maps {
  CUtensorMap x, wm, wt, k, v, y, wo, qm, qt, om, ot, u;
};

__device__ __forceinline__ void load_stage(uint32_t sb, int kb, int b, const Maps& m) {
  const uint32_t st = sb + (kb & 3) * STAGE_BYTES, bar = sb + OFF_BAR + 8 * (B_FULL1 + (kb & 3));
  const int r = b >> 3, hg = b & 7, slab = kb - KV_KB;
  const bool kv = slab >= 0 && slab < 5;
  const uint32_t kbar = sb + OFF_BAR + 8 * (B_KV + slab), dst = sb + OFF_KVS + slab * KVS_BYTES;
  mbar_expect_tx(bar, STAGE_BYTES);
  if (kv) mbar_expect_tx(kbar, KVS_BYTES);
  tma_3d(st, &m.x, 64 * kb, 64 * r, 0, bar);
  if (kv && KV_MIX) tma_3d(dst, &m.k, 0, 32 * (b >> 1) - 3, 2 * slab + (b & 1), kbar);
  tma_3d(st + ST_W, &m.wm, 80 * hg + (tail_first(hg) ? 16 : 0), 64 * kb, 0, bar);
  if (kv && KV_MIX) tma_3d(dst + KVS_V, &m.v, 0, 32 * (b >> 1), 2 * slab + (b & 1), kbar);
  tma_3d(st + ST_WT, &m.wt, 80 * hg + (tail_first(hg) ? 0 : 64), 64 * kb, 0, bar);
  if (kv && !KV_MIX) tma_3d(dst, &m.k, 0, 32 * (b >> 1) - 3, 2 * slab + (b & 1), kbar);
  if (kv && !KV_MIX) tma_3d(dst + KVS_V, &m.v, 0, 32 * (b >> 1), 2 * slab + (b & 1), kbar);
}

__global__ void __launch_bounds__(NTHR, 1) fused_kernel(const __grid_constant__ Maps m, const Params p) {
  extern __shared__ __align__(1024) uint8_t smem[];
  const uint32_t sb = (uint32_t)__cvta_generic_to_shared(smem);
  const uint32_t bars = sb + OFF_BAR;
  const int tid = threadIdx.x, lane = tid & 31;
  int b = blockIdx.x;
  if (BMAP == 1) b = (((b & 63) >> 3) * 2 + (b & 1)) * 8 + (((b < 64 ? 0x6521 : 0x7430) >> (4 * ((b >> 1) & 3))) & 7);
  if (BMAP == 2) b = ((b & 63) >> 2) * 8 + (((b < 64 ? 0x6521 : 0x7430) >> (4 * (b & 3))) & 7);
  if (BMAP == 3) b = (((b & 63) >> 3) * 2 + (b & 1)) * 8 + (((b < 64 ? 0x7430 : 0x6521) >> (4 * ((b >> 1) & 3))) & 7);
  if (BMAP == 4) b = (((b >> 4) * 2 + (b & 1)) * 8) + ((b >> 1) & 7);
  if (BMAP == 5) b = 127 - b;
  const int r = b >> 3, hg = b & 7;

  if (tid == T_ISSUE) {
    TSM(true, 0);
#pragma unroll
    for (int i = 0; i < 4; i++) mbar_init(bars + 8 * (B_FULL1 + i), 1);
#pragma unroll
    for (int i = 0; i < 3; i++) mbar_init(bars + 8 * (B_KV + i), 1);
    fence_async_smem();
#pragma unroll 1
    for (int kb = 0; kb <= PRE2; kb++) load_stage(sb, kb, b, m);
  } else if (tid >= T_PF && tid < T_PF + 12) {
    tm_prefetch(&m.x + (tid - T_PF));
  } else if (tid == T_INIT) {
#pragma unroll
    for (int i = 0; i < 4; i++) mbar_init(bars + 8 * (B_EMPTY1 + i), 8);
#pragma unroll
    for (int i = 0; i < 8; i++) mbar_init(bars + 8 * (B_FULL2 + i), 1);
#pragma unroll
    for (int i = 0; i < 4; i++) mbar_init(bars + 8 * (B_EMPTY2 + i), 8);
#pragma unroll
    for (int i = 0; i < 4; i++) mbar_init(bars + 8 * (B_U + i), 1);
    mbar_init(bars + 8 * B_HA, 4);
    mbar_init(bars + 8 * B_GATE, 4);
    mbar_init(bars + 8 * B_HB, 1);
    mbar_init(bars + 8 * B_KVD, 4);
    mbar_init(bars + 8 * B_QF, 1);
    mbar_init(bars + 8 * B_ATTN, 8);
    mbar_init(bars + 8 * B_ATT2, 8);
    mbar_init(bars + 8 * B_P1, 8);
    mbar_init(bars + 8 * B_C34, 1);
    mbar_init(bars + 8 * B_YRB, 1);
#pragma unroll
    for (int i = 0; i < 5; i++) mbar_init(bars + 8 * (B_YST + i), 4);
#pragma unroll
    for (int i = 0; i < 5; i++) mbar_init(bars + 8 * (B_US + i), U_TMA ? 4 : 1);
    mbar_init(bars + 8 * B_YSIG, 1);
    mbar_init(bars + 8 * B_YFULL, 1);
    mbar_init(bars + 8 * B_EPOCH, 1);
    mbar_init(bars + 8 * B_PREP, 4);
    mbar_init(bars + 8 * B_USIG, 1);
    mbar_init(bars + 8 * B_WST, 1);
#pragma unroll
    for (int i = 3; i < 5; i++) mbar_init(bars + 8 * (B_KV + i), 1);
    mbar_init(bars + 8 * B_E3, 8);
    mbar_init(bars + 8 * B_LAST, 1);
    mbar_init(bars + 8 * B_OSIG, 1);
    mbar_init(bars + 8 * B_WOP, 1);
    fence_async_smem();
  }
  const int warp = __shfl_sync(0xffffffffu, tid >> 5, 0), wg = warp >> 2, w = warp & 3;
  __syncthreads();

  if (wg == 3) {
    asm volatile("setmaxnreg.dec.sync.aligned.u32 56;");
    if (w == 0) {
      if (lane == 0) {
#pragma unroll 1
        for (int kb = 1 + PRE2; kb < 10; kb++) {
          if (kb >= 4) mbar_wait(bars + 8 * (kb == 7 ? B_E3 : B_EMPTY1 + (kb & 3)), (kb >> 3) & 1);
          TSIF(kb >= 4, 44 + kb);
          load_stage(sb, kb, b, m);
          TSIF(kb == 3, 60);
          if (kb == TRIG_KB) mbar_arrive(bars + 8 * B_LAST);
        }
        mbar_wait(bars + 8 * B_WOP, 0);
        mbar_wait(bars + 8 * WL_TRIG, 0);
        mbar_wait(bars + 8 * B_EPOCH, 0);
        flag_wait(g_cnt + C_W + 32 * hg, (lds32(sb + OFF_EPOCH) + 1) * 16);
        TS(30);
#pragma unroll 1
        for (int j = 0; j < 8; j++) {
          if (j >= 6) mbar_wait(bars + 8 * (B_EMPTY2 + j - 6), 0);
          if (j == 4) mbar_wait(bars + 8 * B_ATTN, 0);
          TSIF(j >= 6, 100 + j);
          if (RF_GATE && j == 6) mbar_wait(bars + 8 * B_YSIG, 0);
          mbar_expect_tx(bars + 8 * (B_FULL2 + j), j == 0 ? WO_BYTES : j == 5 ? O_BYTES + WO_BYTES + 512 : O_BYTES + WO_BYTES);
          bulk_load(sb + off_w(j), g_WO + (hg * 8 + step_src(hg, j)) * 800, WO_BYTES, bars + 8 * (B_FULL2 + j));
        }
        mbar_wait(bars + 8 * (B_EMPTY2 + Q_SLOT), 0);
        mbar_expect_tx(bars + 8 * B_QF, O_BYTES);
        tma_2d(sb + OFF_QS, &m.qm, 80 * hg, 128 * r, bars + 8 * B_QF);
        tma_2d(sb + OFF_QT, &m.qt, 80 * hg + 64, 128 * r, bars + 8 * B_QF);
      }
    } else if (w == 1) {
      unsigned epoch = 0;
      if (lane == 0) {
        epoch = atomicAdd(g_cnt + C_LAUNCH, 1u) / NCTA;
        asm volatile("st.shared.u32 [%0], %1;" ::"r"(sb + OFF_EPOCH), "r"(epoch) : "memory");
        mbar_arrive(bars + 8 * B_EPOCH);
        mbar_wait(bars + 8 * B_KVD, 0);
        mbar_expect_tx(bars + 8 * B_HB, 5 * 4096);
#pragma unroll 1
        for (int c = 0; c < 5; c++) {
          if (c == 3) mbar_wait(bars + 8 * B_S3, 0);
          bulk_load(sb + off_ch(c) + U_BYTES, p.ssm_k + (5 * b + c) * SEQ, 4096, bars + 8 * B_HB);
        }
#pragma unroll
        for (int c = 0; c < 4; c++) mbar_expect_tx(bars + 8 * (B_U + c), c < 3 ? U_BYTES : 2 * U_BYTES);
        const uint4* usrc = g_U + 5 * b * U_PITCH;
        mbar_wait(bars + 8 * B_USIG, 0);
        flag_wait(g_cnt + C_PREP + 32 * (b & 15), (epoch + 1) * NCTA);
        TS(23);
#pragma unroll
        for (int c = 0; c < 5; c++) {
          if (c == 3 && U_TRIM) mbar_wait(bars + 8 * (B_U + 2), 0);
          bulk_load(sb + off_ch(c), usrc + c * U_PITCH, U_BYTES, bars + 8 * (B_U + (c < 3 ? c : 3)));
          TSIF(c == 0 || c == 4, 116 + (c >> 2));
        }
      }
      epoch = __shfl_sync(0xffffffffu, epoch, 0);
      if (lane < 8) {
        const int src = (b & ~7) | step_src(hg, lane);
        mbar_wait(bars + 8 * OP_TRIG, 0);
        TS(20);
        bool seen = false;
#pragma unroll 1
        for (int spins = 0; spins < SPIN_LIMIT; spins++) {
          const bool now = !seen && (int)(flag_read(g_cnt + C_O + 32 * src) - (epoch + 1)) >= 0;
          if (now && lane >= 1 && lane < 4) bulk_load(sb + off_o(lane), g_O + src * 1280, O_BYTES, bars + 8 * (B_FULL2 + lane));
          seen = seen || now;
          if (__all_sync(0xff, seen)) break;
        }
        TS(21);
        if (lane == 5) bulk_load(sb + OFF_GATE, g_gate + 128 * r, 512, bars + 8 * (B_FULL2 + 5));
#pragma unroll 1
        for (int j = 4; j < 8; j++) {
          if (lane == j) {
            mbar_wait(bars + 8 * (j < 6 ? B_C34 : B_EMPTY2 + j - 6), 0);
            if (RF_GATE && j == 6) mbar_wait(bars + 8 * B_YSIG, 0);
            bulk_load(sb + off_o(j), g_O + src * 1280, O_BYTES, bars + 8 * (B_FULL2 + j));
          }
          __syncwarp(0xff);
        }
        TS(22);
      }
    } else if (w == 2) {
      mbar_wait(bars + 8 * B_PREP, 0);
      flag_signal(g_cnt + C_PREP, 16, lane);
      TS(25);
      if (lane == 0) mbar_arrive(bars + 8 * B_USIG);
      mbar_wait(bars + 8 * B_GATE, 0);
      if (G_TMA) {
        if (lane == 0) {
          asm volatile("cp.async.bulk.global.shared::cta.bulk_group [%0], [%1], 64;\ncp.async.bulk.commit_group;\n"
                       "cp.async.bulk.wait_group.read 0;" ::"l"(g_gate + 16 * b), "r"(sb + OFF_GATE + 64 * hg) : "memory");
          bulk_load(sb + OFF_GATE + 64 * hg, g_gate + 16 * b, 64, bars + 8 * B_ORB);
        }
      } else if (((NOMB & 1) || O_RB) && lane == 0) {
        asm volatile("fence.release.gpu;" ::: "memory");
      }
      mbar_wait(bars + 8 * B_ATTN, 0);
      if (lane == 0) {
        if (O_DEFER) mbar_wait(bars + 8 * (B_U + 3), 0);
        asm volatile("cp.async.bulk.global.shared::cta.bulk_group [%0], [%1], 20480;\ncp.async.bulk.commit_group;"
                     ::"l"(g_O + b * 1280), "r"(sb + OFF_OA) : "memory");
        if (O_RB == 2) {
          asm volatile("cp.async.bulk.wait_group.read 0;" ::: "memory");
          mbar_expect_tx(bars + 8 * B_ORB, O_BYTES + 64 * G_TMA);
          bulk_load(sb + OFF_OA, g_O + b * 1280, O_BYTES, bars + 8 * B_ORB);
          mbar_wait(bars + 8 * B_ORB, 0);
          flag_bump(g_cnt + C_O + 32 * b);
        } else if (O_RB) asm volatile("cp.async.bulk.wait_group.read 0;" ::: "memory");
        else asm volatile("cp.async.bulk.wait_group 0;\nfence.proxy.async.global;" ::: "memory");
      }
      TS(74);
      if (O_RB == 2) {
      } else if (O_RB) {
        __syncwarp();
        unsigned v[5];
#pragma unroll
        for (int c = 0; c < 5; c++) v[c] = flag_read(reinterpret_cast<const unsigned*>(g_O + b * 1280 + 256 * c + 8 * lane + 7));
        const unsigned dep = __reduce_or_sync(0xffffffffu, (v[0] ^ v[1] ^ v[2] ^ v[3] ^ v[4]) & p.zero);
        if (lane == 0) flag_bump(g_cnt + C_O + 32 * b + dep);
      } else if (!(NOMB & 1)) flag_signal(g_cnt + C_O + 32 * b, 1, lane);
      else if (lane == 0) flag_bump(g_cnt + C_O + 32 * b);
      TS(26);
      if (lane == 0) mbar_arrive(bars + 8 * B_OSIG);

    } else {
      if (lane == 0) {
        uint4* dst = g_WO + (hg * 8 + (r >> 1)) * 800 + (r & 1) * 80;
        if (WPF) {
          mbar_wait(bars + 8 * WPF, 0);
          if (WPF_LIN)
            asm volatile("cp.async.bulk.prefetch.L2.global [%0], 6400;" ::"l"(p.wo + b * 3200) : "memory");
          else
            asm volatile("cp.async.bulk.prefetch.tensor.3d.L2.global [%0, {%1, %2, %3}];" ::"l"(&m.wo), "r"(0), "r"(40 * r), "r"(5 * hg) : "memory");
        }
        mbar_wait(bars + 8 * B_P1, 0);
        mbar_wait(bars + 8 * WB_TRIG, 0);
        mbar_expect_tx(bars + 8 * B_WST, WO_BYTES / 2);
        tma_3d(sb + OFF_WS, &m.wo, 0, 40 * r, 5 * hg, bars + 8 * B_WST);
        mbar_wait(bars + 8 * B_WST, 0);
        mbar_wait(bars + 8 * WO_TRIG, 0);
#pragma unroll 1
        for (int n = 0; n < 5; n++)
          asm volatile("cp.async.bulk.global.shared::cta.bulk_group [%0], [%1], 1280;" ::"l"(dst + 160 * n), "r"(sb + OFF_WS + 1280 * n) : "memory");
        if (W_RB) {
          asm volatile("cp.async.bulk.commit_group;\ncp.async.bulk.wait_group.read 0;" ::: "memory");
          mbar_expect_tx(bars + 8 * B_WST, WO_BYTES / 2);
#pragma unroll 1
          for (int n = 0; n < 5; n++) bulk_load(sb + OFF_WS + 1280 * n, dst + 160 * n, 1280, bars + 8 * B_WST);
          mbar_wait(bars + 8 * B_WST, 1);
        } else {
          asm volatile("cp.async.bulk.commit_group;\ncp.async.bulk.wait_group 0;\nfence.proxy.async.global;" ::: "memory");
          if (!(NOMB & 4)) asm volatile("fence.release.gpu;" ::: "memory");
        }
        flag_bump(g_cnt + C_W + 32 * hg);
        mbar_arrive(bars + 8 * B_WOP);
        TS(71);
        mbar_expect_tx(bars + 8 * B_C34, 3 * U_BYTES);
        mbar_expect_tx(bars + 8 * B_YRB, 2 * U_BYTES);
#pragma unroll 1
        for (int c = 0; c < 5; c++) {
          mbar_wait(bars + 8 * (B_YST + c), 0);
          asm volatile("cp.async.bulk.global.shared::cta.bulk_group [%0], [%1], 4096;\ncp.async.bulk.commit_group;\n"
                       "cp.async.bulk.wait_group.read 0;" ::"l"(g_Y + (5 * b + c) * Y_PITCH), "r"(sb + off_ch(c)) : "memory");
          bulk_load(sb + off_ch(c), g_Y + (5 * b + c) * Y_PITCH, U_BYTES, bars + 8 * (c < 3 ? B_C34 : B_YRB));
        }
        TS(75);
        mbar_wait(bars + 8 * B_C34, 0);
        mbar_wait(bars + 8 * B_YRB, 0);
        flag_bump(g_cnt + C_Y + 32 * (b >> 4));
        TS(27);
        mbar_arrive(bars + 8 * B_YSIG);
        mbar_expect_tx(bars + 8 * B_YFULL, 20480);
        flag_wait(g_cnt + C_Y + 32 * hg, (lds32(sb + OFF_EPOCH) + 1) * 16);
        TS(24);
        tma_2d(sb + OFF_YT, &m.y, 128 * r, 80 * hg, bars + 8 * B_YFULL);
        tma_2d(sb + OFF_YT + 10240, &m.y, 128 * r + 64, 80 * hg, bars + 8 * B_YFULL);
      }
    }
  } else {
    asm volatile("setmaxnreg.inc.sync.aligned.u32 152;");
    if (wg < 2) {
      float acc[120];
#pragma unroll
      for (int i = 0; i < 120; i++) acc[i] = 0.f;
      const uint32_t da = desc_lo(sb + wg * 8192, 16), db = desc_lo(sb + ST_W, 8192), dc = desc_lo(sb + ST_WT, 2048);
      if (PW1) pin<120>(acc);
      if (PW1 == 2) mbar_wait(bars + 8 * B_FULL1, 0);
#pragma unroll 1
      for (int kb = 0; kb < 10; kb++) {
        mbar_wait(bars + 8 * (B_FULL1 + (kb & 3)), (kb >> 2) & 1);
        const uint32_t so = (kb & 3) * (STAGE_BYTES >> 4);
        wg_fence();
#pragma unroll
        for (int k = 0; k < 4; k++) {
          WgSST<192>::mma<HI_SW128, HI_SW128>(acc, da + so + 2 * k, db + so + 128 * k, 1);
          WgSST<48>::mma<HI_SW128, HI_SW32>(acc + 96, da + so + 2 * k, dc + so + 32 * k, 1);
        }
        wg_commit();
        wg_wait<1>();
        if (kb > 0 && lane == 0) mbar_arrive(bars + 8 * (kb == 4 ? B_E3 : B_EMPTY1 + ((kb - 1) & 3)));
      }
      mbar_wait(bars + 8 * B_EPOCH, 0);
      const uint32_t tag = lds32(sb + OFF_EPOCH) + 1;
      mbar_wait(bars + 8 * B_S3, 0);
      wg_wait<0>();
      pin<120>(acc);
      if (lane == 0) mbar_arrive(bars + 8 * B_P1);
      TSM(w == 0, 3 + wg);
      attention(acc, sb, b, wg, w, lane, tag, p.zero);
    } else {
      const int tw = tid & 127, chl = 64 * (b & 1) + 8 * w + (lane >> 2);
      uint4* up = g_U + chl * U_PITCH + ((4 * (b >> 1) + (lane & 3)) ^ ((b >> 2) & 1));
      uint2 sw[10];
      uint32_t dv = 0;
      if (lane < 5) dv = __ldg(reinterpret_cast<const unsigned short*>(p.ssm_D) + 5 * b + lane);
#pragma unroll
      for (int i = 0; i < 10; i++) sw[i] = ldg64(reinterpret_cast<const uint2*>(p.shift_k) + chl + 128 * (i >> 1) + 32 * (i & 1));
      uint32_t tab[12];
      uint32_t tt[2];
      fft_tables(tab, tw);
      fft_twiddles(tt, tw);
      uint4 res[10];
#pragma unroll
      for (int i = 0; i < 10; i++) res[i] = make_uint4(0, 0, 0, 0);
#pragma unroll 1
      for (int slab = 0; slab < 5; slab++) {
#pragma unroll
        for (int i = 0; i < 8; i++) res[i] = res[i + 2];
        prep_slab(res + 8, sw, sb, slab, w, lane);
        TSIF(w == 0, 99 + 4 * slab);
#pragma unroll
        for (int i = 0; i < 8; i++) sw[i] = sw[i + 2];
      }
      TSIF(w == 0, 28);
      __syncwarp();
      if (lane == 0) mbar_arrive(bars + 8 * B_KVD + ((res[8].x ^ res[9].x) & p.zero));
      mbar_wait(bars + 8 * B_KVD, 0);
      fft_tables_store(tab, sb, tw);
      mbar_wait(bars + 8 * B_LAST, 0);
#pragma unroll
      for (int i = 0; i < 10; i++) up[(128 * (i >> 1) + 32 * (i & 1)) * U_PITCH] = res[i];
      __syncwarp();
      if (lane == 0) mbar_arrive(bars + 8 * B_PREP);
      TSIF(w == 0 && !U_TMA, 5);
      mbar_wait(bars + 8 * (G_AFTER ? B_USIG : B_LAST), 0);
      prep_gate(p, sb, b, w, lane);
      __syncwarp();
      if (lane == 0) mbar_arrive(bars + 8 * B_GATE);
      TSIF(w == 0, 72);
      mbar_wait(bars + 8 * B_HB, 0);
      TSIF(w == 0, 2);
      const uint32_t ha = sb + U_BYTES + ((tw >> 3) * 16 + 8 + (tw & 7)) * 16;
      uint4 hv[5];
#pragma unroll
      for (int c = 0; c < 5; c++) hv[c] = lds128(ha + off_ch(c));
      __syncwarp();
#pragma unroll
      for (int c = 0; c < 5; c++) sts128((ha ^ 16) + off_ch(c), hv[c].x, hv[c].y, hv[c].z, hv[c].w);
      asm volatile("st.shared.v2.u32 [%0], {%1, %2};" ::"r"(sb + OFF_TT + 8 * tw), "r"(tt[0]), "r"(tt[1]) : "memory");
      if (tw < 5) asm volatile("st.shared.f32 [%0], %1;" ::"r"(sb + OFF_D + 4 * tw), "f"(bf_lo(dv) * 0.125f) : "memory");
      fence_async_smem();
      __syncwarp();
      if (lane == 0) mbar_arrive(bars + 8 * B_HA);
      TSIF(w == 0, 6);
    }

    FftConst fc;
    TSM(w == 0 && wg == 0, 104);
    mbar_wait(bars + 8 * B_HA, 0);
    fft_matrices(fc, sb, w, lane);
    TSM(w == 0 && wg == 0, 105);
    TSM(w == 0 && wg == 2, 124);
#pragma unroll 1
    for (uint32_t tasks = wg == 0 ? TASK0 : wg == 1 ? TASK1 : TASK2; tasks; tasks >>= 4) {
      const int c = (tasks & 7) - 1;
      conv_channel(fc, sb, c, wg, w, lane);
      if (lane == 0) mbar_arrive(bars + 8 * (B_YST + c));
      TSM(w == 0, 10 + c);
    }

    if (wg < 2) {
      const int g = lane >> 2;
      float acc[40];
#pragma unroll
      for (int i = 0; i < 40; i++) acc[i] = 0.f;
      const uint32_t da = desc_lo(sb + wg * 1024, 2048), db = desc_lo(sb, 2560);
      if (!WO_FAST) mbar_wait(bars + 8 * (O_RB == 2 ? B_ORB : B_ATTN), 0);
      mbar_wait(bars + 8 * (B_YST + 3), 0);
      mbar_wait(bars + 8 * (B_YST + 4), 0);
      if (PW2 && !WO_FAST) mbar_wait(bars + 8 * B_FULL2, 0);
      TSM(w == 0, 15 + wg);
#pragma unroll 1
      for (int j = 0; j < 8; j++) {
        mbar_wait(bars + 8 * (B_FULL2 + j), 0);
        const uint32_t oa = da + (off_o(j) >> 4), ob = db + (off_w(j) >> 4);
        wg_fence();
#pragma unroll
        for (int k = 0; k < 5; k++) WgSST<80>::mma<HI_NONE, HI_SW32>(acc, oa + 256 * k, ob + 32 * k, 1);
        wg_commit();
        wg_wait<1>();
        if (j >= 1 && j <= Q_SLOT + 1 && lane == 0) mbar_arrive(bars + 8 * (B_EMPTY2 + j - 1));
      }
      TSIF(w == 0 && wg == 0, 113);
      const int tr = 64 * wg + 16 * w + (lane & 15);
      const uint32_t fm = sb + OFF_QS + tr * 128, fx = (lane >> 4) ^ (tr & 7);
      const uint32_t ft = sb + OFF_QT + tr * 32 + (((lane >> 4) ^ (tr >> 2)) & 1) * 16;
      const float g0 = __uint_as_float(lds32(sb + OFF_GATE + (64 * wg + 16 * w + g) * 4));
      const float g1 = __uint_as_float(lds32(sb + OFF_GATE + (64 * wg + 16 * w + 8 + g) * 4));
      const uint32_t ga = pack2(g0, g0), gb = pack2(g1, g1);
      const uint32_t na = pack2(1.f - g0, 1.f - g0), nb = pack2(1.f - g1, 1.f - g1);

      uint32_t qf[20];
      mbar_wait(bars + 8 * B_QF, 0);
#pragma unroll
      for (int j = 0; j < 5; j++) ldsm4(qf + 4 * j, j < 4 ? fm + ((fx ^ (2 * j)) << 4) : ft);
      if (FUSE_MIX) {
#pragma unroll
        for (int i = 0; i < 20; i++) {
          qf[i] = bmul((i & 1) ? gb : ga, qf[i]);
          asm volatile("" : "+r"(qf[i]));
        }
      }
      wg_wait<0>();
      pin<40>(acc);
      TSM(w == 0, 17 + wg);
      uint32_t pb[20];
#pragma unroll
      for (int j = 0; j < 10; j++) {
        pb[2 * j] = bmul(na, pack2(acc[4 * j], acc[4 * j + 1]));
        pb[2 * j + 1] = bmul(nb, pack2(acc[4 * j + 2], acc[4 * j + 3]));
        asm volatile("" : "+r"(pb[2 * j]), "+r"(pb[2 * j + 1]));
      }
      const uint32_t ya = sb + OFF_YT + wg * 10240 + ((lane >> 4) * 8 + (lane & 7)) * 128 +
                          (((2 * w + (((lane >> 3) & 1) ^ wg)) ^ (lane & 7)) << 4);
      mbar_wait(bars + 8 * B_YFULL, 0);
      TSM(w == 0 && wg == 0, 19);
#pragma unroll
      for (int j = 0; j < 5; j++) {
        uint32_t y[4];
        ldsm4t(y, ya + 2048 * j);
#pragma unroll
        for (int i = 0; i < 4; i++)
          qf[4 * j + i] = FUSE_MIX ? bfma(qf[4 * j + i], y[i], pb[4 * j + i]) : badd(bmul((i & 1) ? gb : ga, bmul(qf[4 * j + i], y[i])), pb[4 * j + i]);
      }
#pragma unroll
      for (int j = 0; j < 5; j++) stsm4(j < 4 ? fm + ((fx ^ (2 * j)) << 4) : ft, qf + 4 * j);
      fence_async_smem();
      __syncwarp();
      if (lane == 0) {
        const int row = 64 * wg + 16 * w;
        asm volatile("cp.async.bulk.tensor.2d.global.shared::cta.bulk_group [%0, {%2, %3}], [%1];"
                     ::"l"(&m.om), "r"(sb + OFF_QS + row * 128), "r"(80 * hg), "r"(128 * r + row) : "memory");
        asm volatile("cp.async.bulk.tensor.2d.global.shared::cta.bulk_group [%0, {%2, %3}], [%1];"
                     ::"l"(&m.ot), "r"(sb + OFF_QT + row * 32), "r"(80 * hg + 64), "r"(128 * r + row) : "memory");
        asm volatile("cp.async.bulk.commit_group;\ncp.async.bulk.wait_group.read 0;" ::: "memory");
      }
      TSM(true, 40 + 4 * wg + w);
      if (ENDBAR) asm volatile("bar.sync 15, 256;" ::: "memory");
    }
  }
}

typedef CUresult (*EncodeFn)(CUtensorMap*, CUtensorMapDataType, cuuint32_t, void*, const cuuint64_t*, const cuuint64_t*,
                             const cuuint32_t*, const cuuint32_t*, CUtensorMapInterleave, CUtensorMapSwizzle,
                             CUtensorMapL2promotion, CUtensorMapFloatOOBfill);

void encode(EncodeFn fn, CUtensorMap* tm, const void* base, int rank, const cuuint64_t* dims, const cuuint64_t* strides,
            const cuuint32_t* box, CUtensorMapSwizzle swz) {
  const cuuint32_t ones[3] = {1, 1, 1};
  fn(tm, CU_TENSOR_MAP_DATA_TYPE_BFLOAT16, rank, const_cast<void*>(base), dims, strides, box, ones,
     CU_TENSOR_MAP_INTERLEAVE_NONE, swz, CU_TENSOR_MAP_L2_PROMOTION_L2_128B, CU_TENSOR_MAP_FLOAT_OOB_FILL_NONE);
}

}

extern "C" void kernel_launch(void* const* d_in, const int* in_sizes, int n_in, void* d_out, int out_size) {
  (void)in_sizes; (void)n_in; (void)out_size;
  Params p;
  p.q = (const __nv_bfloat16*)d_in[0];
  p.k = (const __nv_bfloat16*)d_in[1];
  p.v = (const __nv_bfloat16*)d_in[2];
  p.shift_k = (const __nv_bfloat16*)d_in[3];
  p.ssm_k = (const __nv_bfloat16*)d_in[4];
  p.ssm_D = (const __nv_bfloat16*)d_in[5];
  p.wqkv = (const __nv_bfloat16*)d_in[7];
  p.wo = (const __nv_bfloat16*)d_in[8];
  p.gate_w = (const __nv_bfloat16*)d_in[9];
  p.out = (__nv_bfloat16*)d_out;
  p.zero = 0;

  static EncodeFn fn = nullptr;
  static void *yaddr = nullptr, *uaddr = nullptr;
  if (!fn) {
    cudaDriverEntryPointQueryResult qr;
    void* f = nullptr;
    cudaGetDriverEntryPoint("cuTensorMapEncodeTiled", &f, cudaEnableDefault, &qr);
    fn = (EncodeFn)f;
    cudaGetSymbolAddress(&yaddr, g_Y);
    cudaGetSymbolAddress(&uaddr, g_U);
    cudaFuncSetAttribute(fused_kernel, cudaFuncAttributeMaxDynamicSharedMemorySize, SMEM_BYTES);
  }
  Maps m;
  {
    const cuuint64_t dims[3] = {640, 1024, 2}, st[2] = {2560, 1280};
    const cuuint32_t box[3] = {64, 64, 2};
    encode(fn, &m.x, p.q, 3, dims, st, box, CU_TENSOR_MAP_SWIZZLE_128B);
  }
  {
    const cuuint64_t dims[3] = {640, 640, 3}, st[2] = {3840, 1280};
    const cuuint32_t box[3] = {64, 64, 3}, boxt[3] = {16, 64, 3};
    encode(fn, &m.wm, p.wqkv, 3, dims, st, box, CU_TENSOR_MAP_SWIZZLE_128B);
    encode(fn, &m.wt, p.wqkv, 3, dims, st, boxt, CU_TENSOR_MAP_SWIZZLE_32B);
  }
  {
    const cuuint64_t dims[3] = {64, 2048, 10}, st[2] = {1280, 128};
    const cuuint32_t boxk[3] = {64, 35, 1}, boxv[3] = {64, 32, 1};
    encode(fn, &m.k, p.k, 3, dims, st, boxk, CU_TENSOR_MAP_SWIZZLE_128B);
    encode(fn, &m.v, p.v, 3, dims, st, boxv, CU_TENSOR_MAP_SWIZZLE_128B);
  }
  {
    const cuuint64_t dims[3] = {16, 640, 40}, st[2] = {1280, 32};
    const cuuint32_t box[3] = {16, 40, 5};
    encode(fn, &m.wo, p.wo, 3, dims, st, box, CU_TENSOR_MAP_SWIZZLE_32B);
  }
  {
    const cuuint64_t dims[2] = {2048, 640}, st[1] = {Y_PITCH * 16};
    const cuuint32_t box[2] = {64, 80};
    encode(fn, &m.y, yaddr, 2, dims, st, box, CU_TENSOR_MAP_SWIZZLE_128B);
    const cuuint64_t stu[1] = {U_PITCH * 16};
    const cuuint32_t boxu[2] = {32, 64};
    encode(fn, &m.u, uaddr, 2, dims, stu, boxu, CU_TENSOR_MAP_SWIZZLE_NONE);
  }
  {
    const cuuint64_t dims[2] = {640, 2048}, st[1] = {1280};
    const cuuint32_t bqm[2] = {64, 128}, bqt[2] = {16, 128}, bom[2] = {64, 16}, bot[2] = {16, 16};
    encode(fn, &m.qm, p.q, 2, dims, st, bqm, CU_TENSOR_MAP_SWIZZLE_128B);
    encode(fn, &m.qt, p.q, 2, dims, st, bqt, CU_TENSOR_MAP_SWIZZLE_32B);
    encode(fn, &m.om, p.out, 2, dims, st, bom, CU_TENSOR_MAP_SWIZZLE_128B);
    encode(fn, &m.ot, p.out, 2, dims, st, bot, CU_TENSOR_MAP_SWIZZLE_32B);
  }
  fused_kernel<<<NCTA, NTHR, SMEM_BYTES>>>(m, p);
}
```

```cpp
#include <cuda.h>
#include <cuda_bf16.h>
#include <cuda_runtime.h>
#include <stdint.h>

namespace {

constexpr int SEQ = 2048, DIM = 640, NCTA = 128, NTHR = 512;

#define TRIG_KB 9
#define KV_KB 2
#define DEV_EXIT 0
#define ATT_GATE 0
#define G_AFTER 0
#define FENCE_LO 0
#define FENCE_HI 0
#define PW1 2
#define PW2 1
#define ENDBAR 0
#define PAD_KB 0
#define Y_ALIAS 1
#define NOMB 0
#define SRC_ROT 0
#define WAIT_NS 0
#define WB_TRIG B_USIG
#define G_POS 0
#define TAILF 1
#define T_ISSUE 384
#define T_PF 416
#define T_INIT 448
#define ATT_MERGE 0
#define BMAP 1
#define PRE2 1
#define KV_MIX 0
#define O_DEFER 0
#define TASK0 0x52
#define TASK1 0x3
#define TASK2 0x41
#define HALO_FIRST 1
#define PREV_EARLY 0
#define Y_RB 2
#define O_RB 2
#define O_EAGER 1
#define OP_TRIG B_ATTN
#define FUSE_MIX 1
#define Q_EARLY 1
#define WO_FAST 0
#define U_TRIM 1
#define Q_SLOT 3
#define G_TMA 1
#define W_RB 1
#define WPF B_S3
#define WPF_LIN 1
#define QBOX 1
#define ACQ 0
#define U_TMA 0
#define U_GATE 0
#define RF_GATE 0
#define WO_TRIG B_WST
#define WL_TRIG B_WOP
#define WO_GATE 1

constexpr uint32_t STAGE_BYTES = 47104, ST_W = 16384, ST_WT = 40960;
constexpr uint32_t O_BYTES = 20480, WO_BYTES = 12800;
constexpr uint32_t OFF_OA = 0;
constexpr uint32_t OFF_QS = Q_SLOT * O_BYTES, OFF_QT = OFF_QS + 16384;
constexpr uint32_t OFF_WC = 81920;
constexpr uint32_t OFF_WA = 94720;
constexpr uint32_t OFF_GATE = 145920;
constexpr uint32_t OFF_TT = 146432;
constexpr uint32_t OFF_KVX = 148480;
constexpr uint32_t OFF_CH3 = 163840;
constexpr uint32_t CH_BYTES = 12288, U_BYTES = 4096;
constexpr uint32_t OFF_FT = 225280, OFF_GT = 229376;
constexpr uint32_t OFF_CH0 = 188416;
constexpr uint32_t OFF_KVS = OFF_CH0, KVS_V = 4480, KVS_BYTES = 8576;
constexpr uint32_t OFF_WS = OFF_WA;
__device__ __forceinline__ uint32_t off_us(int s) { return OFF_CH0 + 4096 * ((0x65320 >> (4 * s)) & 7); }
constexpr uint32_t OFF_YT = 163840;
constexpr uint32_t OFF_BAR = 231936;
constexpr uint32_t SMEM_BYTES = OFF_BAR + 512;

enum : uint32_t {
  B_FULL1 = 0, B_EMPTY1 = 4, B_S3 = 7, B_FULL2 = 52, B_EMPTY2 = 13, B_U = 8, B_GATE = 12, B_HA = 19, B_HB = 20,
  B_ATTN = 21, B_C34 = 22, B_YRB = 23, B_YFULL = 24, B_EPOCH = 25, B_PREP = 26, B_P1 = 27, B_LAST = 28,
  B_E3 = 29, B_OSIG = 30, B_WOP = 31, B_USIG = 32, B_WST = 33, B_KV = 34, B_KVD = 39, B_QF = 17, B_ATT2 = 18, B_YST = 40,
  B_ORB = 45, B_US = 45, B_YSIG = 50
};
constexpr uint32_t OFF_EPOCH = OFF_BAR + 8 * 51, OFF_D = OFF_BAR + 8 * 60;
__device__ __forceinline__ uint32_t off_o(int j) { return j < 4 ? OFF_OA + j * O_BYTES : j < 6 ? OFF_CH0 + (j - 4) * O_BYTES : OFF_OA + (j - 6) * O_BYTES; }
__device__ __forceinline__ uint32_t off_w(int j) { return j < 4 ? OFF_WA + j * WO_BYTES : j == 4 ? OFF_KVX : j == 5 ? OFF_WC : OFF_WA + (j - 6) * WO_BYTES; }
__device__ __forceinline__ int step_src(int hg, int j) {
  if (SRC_ROT == 2) {
    const int pos = (0x37621540 >> (4 * hg)) & 7;
    return j == 0 ? hg : (0x65217430 >> (4 * (j <= pos ? j - 1 : j))) & 7;
  }
  return SRC_ROT ? (hg + j) & 7 : j == 0 ? hg : j <= hg ? j - 1 : j;
}
__device__ __forceinline__ bool tail_first(int hg) { return TAILF && (hg & 3) == 3; }
__device__ __forceinline__ uint32_t off_ch(int c) { return (c < 3 ? OFF_CH0 : OFF_CH3 - 3 * CH_BYTES) + c * CH_BYTES; }

#define U_PITCH 264
__device__ __align__(1024) uint4 g_U[DIM * U_PITCH];
__device__ uint4 g_O[NCTA * 1280];
#define g_Y g_U
constexpr int Y_PITCH = U_PITCH;
__device__ uint4 g_WO[64 * 800];
__device__ uint4 g_halo[NCTA * 2 * 7 * 32];
__device__ __align__(128) float g_gate[SEQ + PAD_KB * 256];
__device__ unsigned g_cnt[32 * (1 + 2 * 16 + 8 + NCTA)];
constexpr int C_LAUNCH = 0, C_PREP = 32, C_Y = 32 * 17, C_W = 32 * 33, C_O = 32 * 41;

#define TSM(cond, slot) do { } while (0)
#define TSIF(cond, slot) do { if (__LINE__ >= FENCE_LO && __LINE__ < FENCE_HI) sched_fence(); } while (0)
__device__ __forceinline__ void sched_fence() {
  asm volatile("{\n.reg .pred p;\n.reg .u32 c;\nmov.u32 c, %%clock;\nsetp.eq.u32 p, c, 0;\n@p st.shared.u32 [%0], c;\n}"
               ::"r"(1024 + OFF_EPOCH + 4) : "memory");
}
#define TS(slot) TSIF(true, slot)

struct Params {
  const __nv_bfloat16 *q, *k, *v, *shift_k, *ssm_k, *ssm_D, *wqkv, *wo, *gate_w;
  __nv_bfloat16* out;
  uint32_t zero;
};

#define POLL_NS 0
constexpr int SPIN_LIMIT = 1 << 17;

__device__ __forceinline__ void mbar_init(uint32_t bar, uint32_t count) {
  asm volatile("mbarrier.init.shared::cta.b64 [%0], %1;" ::"r"(bar), "r"(count) : "memory");
}
__device__ __forceinline__ void mbar_expect_tx(uint32_t bar, uint32_t bytes) {
  asm volatile("mbarrier.arrive.expect_tx.shared::cta.b64 _, [%0], %1;" ::"r"(bar), "r"(bytes) : "memory");
}
__device__ __forceinline__ void mbar_arrive(uint32_t bar) {
  asm volatile("mbarrier.arrive.shared::cta.b64 _, [%0];" ::"r"(bar) : "memory");
}
__device__ __forceinline__ void mbar_wait(uint32_t bar, uint32_t parity) {
  uint32_t ok;
  int spins = 0;
  do {
    if (WAIT_NS)
      asm volatile("{\n.reg .pred p;\nmbarrier.try_wait.parity.shared::cta.b64 p, [%1], %2, %3;\nselp.b32 %0, 1, 0, p;\n}"
                   : "=r"(ok) : "r"(bar), "r"(parity), "r"(WAIT_NS) : "memory");
    else
      asm volatile("{\n.reg .pred p;\nmbarrier.try_wait.parity.shared::cta.b64 p, [%1], %2;\nselp.b32 %0, 1, 0, p;\n}"
                   : "=r"(ok) : "r"(bar), "r"(parity) : "memory");
    if (++spins > SPIN_LIMIT) break;
  } while (!ok);
}
__device__ __forceinline__ unsigned flag_read(const unsigned* p) {
  unsigned v;
  asm volatile("ld.relaxed.gpu.global.u32 %0, [%1];" : "=r"(v) : "l"(p) : "memory");
  return v;
}
__device__ __forceinline__ void flag_poll(const unsigned* p, unsigned target) {
  unsigned v;
  int spins = 0;
  do {
    if (POLL_NS && spins) __nanosleep(POLL_NS);
    asm volatile("ld.relaxed.gpu.global.u32 %0, [%1];" : "=r"(v) : "l"(p) : "memory");
    if (++spins > SPIN_LIMIT) break;
  } while ((int)(v - target) < 0);
}
__device__ __forceinline__ void flag_wait(const unsigned* p, unsigned target) {
  flag_poll(p, target);
  if (ACQ) asm volatile("fence.acquire.gpu;\nfence.proxy.async.global;" ::: "memory");
}
__device__ __forceinline__ void flag_signal(unsigned* p, int n, int lane) {
  if (lane == 0) asm volatile("fence.release.gpu;" ::: "memory");
  __syncwarp();
  if (lane < n) asm volatile("red.relaxed.gpu.global.add.u32 [%0], 1;" ::"l"(p + 32 * lane) : "memory");
}
__device__ __forceinline__ void flag_bump(unsigned* p) {
  asm volatile("red.relaxed.gpu.global.add.u32 [%0], 1;" ::"l"(p) : "memory");
}
__device__ __forceinline__ void fence_async_smem() { asm volatile("fence.proxy.async.shared::cta;" ::: "memory"); }
__device__ __forceinline__ void wg_sync(int id) { asm volatile("bar.sync %0, 128;" ::"r"(id) : "memory"); }

__device__ __forceinline__ void tma_2d(uint32_t dst, const CUtensorMap* tm, int c0, int c1, uint32_t bar) {
  asm volatile("cp.async.bulk.tensor.2d.shared::cluster.global.mbarrier::complete_tx::bytes [%0], [%1, {%3, %4}], [%2];"
               ::"r"(dst), "l"(tm), "r"(bar), "r"(c0), "r"(c1) : "memory");
}
__device__ __forceinline__ void tma_3d(uint32_t dst, const CUtensorMap* tm, int c0, int c1, int c2, uint32_t bar) {
  asm volatile("cp.async.bulk.tensor.3d.shared::cluster.global.mbarrier::complete_tx::bytes [%0], [%1, {%3, %4, %5}], [%2];"
               ::"r"(dst), "l"(tm), "r"(bar), "r"(c0), "r"(c1), "r"(c2) : "memory");
}
__device__ __forceinline__ void bulk_load(uint32_t dst, const void* src, uint32_t bytes, uint32_t bar) {
  asm volatile("cp.async.bulk.shared::cluster.global.mbarrier::complete_tx::bytes [%0], [%1], %2, [%3];"
               ::"r"(dst), "l"(src), "r"(bytes), "r"(bar) : "memory");
}
__device__ __forceinline__ void tm_prefetch(const CUtensorMap* tm) {
  asm volatile("prefetch.tensormap [%0];" ::"l"(tm) : "memory");
}

__device__ __forceinline__ void wg_fence() { asm volatile("wgmma.fence.sync.aligned;" ::: "memory"); }
__device__ __forceinline__ void wg_commit() { asm volatile("wgmma.commit_group.sync.aligned;" ::: "memory"); }
template <int N> __device__ __forceinline__ void wg_wait() { asm volatile("wgmma.wait_group.sync.aligned %0;" ::"n"(N) : "memory"); }
__device__ __forceinline__ uint32_t desc_lo(uint32_t addr, uint32_t lbo) { return ((addr & 0x3FFFF) >> 4) | ((lbo >> 4) << 16); }
constexpr uint32_t desc_hi(uint32_t sbo, uint32_t swz) { return (sbo >> 4) | (swz << 30); }
constexpr uint32_t HI_SW128 = desc_hi(1024, 1), HI_SW64 = desc_hi(512, 2), HI_SW32 = desc_hi(256, 3), HI_NONE = desc_hi(128, 0);
template <int N> __device__ __forceinline__ void pin(float* d) {
#pragma unroll
  for (int i = 0; i < N; i++) asm volatile("" : "+f"(d[i])::"memory");
}

__device__ __forceinline__ uint32_t lds32(uint32_t a) {
  uint32_t v;
  asm volatile("ld.volatile.shared.u32 %0, [%1];" : "=r"(v) : "r"(a) : "memory");
  return v;
}
__device__ __forceinline__ uint4 ldg128(const void* a) {
  uint4 v;
  asm volatile("ld.global.nc.v4.u32 {%0, %1, %2, %3}, [%4];" : "=r"(v.x), "=r"(v.y), "=r"(v.z), "=r"(v.w) : "l"(a) : "memory");
  return v;
}
__device__ __forceinline__ uint2 ldg64(const void* a) {
  uint2 v;
  asm volatile("ld.global.nc.v2.u32 {%0, %1}, [%2];" : "=r"(v.x), "=r"(v.y) : "l"(a) : "memory");
  return v;
}
__device__ __forceinline__ void ldsm4(uint32_t* r, uint32_t a) {
  asm volatile("ldmatrix.sync.aligned.m8n8.x4.shared.b16 {%0, %1, %2, %3}, [%4];"
               : "=r"(r[0]), "=r"(r[1]), "=r"(r[2]), "=r"(r[3]) : "r"(a) : "memory");
}
__device__ __forceinline__ void ldsm4t(uint32_t* r, uint32_t a) {
  asm volatile("ldmatrix.sync.aligned.m8n8.x4.trans.shared.b16 {%0, %1, %2, %3}, [%4];"
               : "=r"(r[0]), "=r"(r[1]), "=r"(r[2]), "=r"(r[3]) : "r"(a) : "memory");
}
__device__ __forceinline__ uint2 lds64(uint32_t a) {
  uint2 v;
  asm volatile("ld.shared.v2.u32 {%0, %1}, [%2];" : "=r"(v.x), "=r"(v.y) : "r"(a) : "memory");
  return v;
}
__device__ __forceinline__ uint4 lds128(uint32_t a) {
  uint4 v;
  asm volatile("ld.shared.v4.u32 {%0, %1, %2, %3}, [%4];" : "=r"(v.x), "=r"(v.y), "=r"(v.z), "=r"(v.w) : "r"(a) : "memory");
  return v;
}
__device__ __forceinline__ void sts128(uint32_t a, uint32_t x, uint32_t y, uint32_t z, uint32_t w) {
  asm volatile("st.shared.v4.u32 [%0], {%1, %2, %3, %4};" ::"r"(a), "r"(x), "r"(y), "r"(z), "r"(w) : "memory");
}
__device__ __forceinline__ void stsm4(uint32_t a, const uint32_t* r) {
  asm volatile("stmatrix.sync.aligned.m8n8.x4.shared.b16 [%0], {%1, %2, %3, %4};" ::"r"(a), "r"(r[0]), "r"(r[1]), "r"(r[2]), "r"(r[3]) : "memory");
}
__device__ __forceinline__ void stsm4t(uint32_t a, const uint32_t* r) {
  asm volatile("stmatrix.sync.aligned.m8n8.x4.trans.shared.b16 [%0], {%1, %2, %3, %4};" ::"r"(a), "r"(r[0]), "r"(r[1]), "r"(r[2]), "r"(r[3]) : "memory");
}
__device__ __forceinline__ uint32_t pack2(float lo, float hi) {
  uint32_t r;
  asm("cvt.rn.bf16x2.f32 %0, %1, %2;" : "=r"(r) : "f"(hi), "f"(lo));
  return r;
}
__device__ __forceinline__ uint32_t movm(uint32_t a) {
  uint32_t d;
  asm volatile("movmatrix.sync.aligned.m8n8.trans.b16 %0, %1;" : "=r"(d) : "r"(a));
  return d;
}
__device__ __forceinline__ uint32_t bmul(uint32_t a, uint32_t b) {
  uint32_t d;
  asm("mul.rn.bf16x2 %0, %1, %2;" : "=r"(d) : "r"(a), "r"(b));
  return d;
}
__device__ __forceinline__ uint32_t badd(uint32_t a, uint32_t b) {
  uint32_t d;
  asm("add.rn.bf16x2 %0, %1, %2;" : "=r"(d) : "r"(a), "r"(b));
  return d;
}
__device__ __forceinline__ uint32_t bfma(uint32_t a, uint32_t b, uint32_t c) {
  uint32_t d;
  asm("fma.rn.bf16x2 %0, %1, %2, %3;" : "=r"(d) : "r"(a), "r"(b), "r"(c));
  return d;
}
__device__ __forceinline__ float bf_lo(uint32_t x) { return __uint_as_float(x << 16); }
__device__ __forceinline__ float bf_hi(uint32_t x) { return __uint_as_float(x & 0xFFFF0000u); }
__device__ __forceinline__ float ex2(float x) {
  float y;
  asm("ex2.approx.ftz.f32 %0, %1;" : "=f"(y) : "f"(x));
  return y;
}
__device__ __forceinline__ float rcp(float x) {
  float y;
  asm("rcp.approx.ftz.f32 %0, %1;" : "=f"(y) : "f"(x));
  return y;
}
__device__ __forceinline__ void mma16816(float* d, uint32_t a0, uint32_t a1, uint32_t a2, uint32_t a3, uint32_t b0, uint32_t b1) {
  asm volatile("mma.sync.aligned.m16n8k16.row.col.f32.bf16.bf16.f32 {%0, %1, %2, %3}, {%4, %5, %6, %7}, {%8, %9}, {%0, %1, %2, %3};"
               : "+f"(d[0]), "+f"(d[1]), "+f"(d[2]), "+f"(d[3])
               : "r"(a0), "r"(a1), "r"(a2), "r"(a3), "r"(b0), "r"(b1));
}
__device__ __forceinline__ void mma1688(float* d, uint32_t a0, uint32_t a1, uint32_t b0) {
  asm volatile("mma.sync.aligned.m16n8k8.row.col.f32.bf16.bf16.f32 {%0, %1, %2, %3}, {%4, %5}, {%6}, {%0, %1, %2, %3};"
               : "+f"(d[0]), "+f"(d[1]), "+f"(d[2]), "+f"(d[3])
               : "r"(a0), "r"(a1), "r"(b0));
}

template <int N> struct WgRS;
template <int N> struct WgSST;
template <> struct WgRS<32> {
  template <uint32_t HB>
  static __device__ __forceinline__ void mma(float* d, const uint32_t* a, uint32_t db) {
    asm volatile("{\n.reg .pred p;\n.reg .b64 db;\nsetp.ne.b32 p, %22, 0;\n"
      "mov.b64 db, {%20, %21};\n"
      "wgmma.mma_async.sync.aligned.m64n32k16.f32.bf16.bf16 {"
      "%0, %1, %2, %3, %4, %5, %6, %7, %8, %9, %10, %11, %12, %13, %14, %15"
      "}, {%16, %17, %18, %19}, db, p, 1, 1, 1;\n}\n"
      : "+f"(d[0]), "+f"(d[1]), "+f"(d[2]), "+f"(d[3]), "+f"(d[4]), "+f"(d[5]), "+f"(d[6]), "+f"(d[7]),
        "+f"(d[8]), "+f"(d[9]), "+f"(d[10]), "+f"(d[11]), "+f"(d[12]), "+f"(d[13]), "+f"(d[14]), "+f"(d[15])
      : "r"(a[0]), "r"(a[1]), "r"(a[2]), "r"(a[3]), "r"(db), "n"(HB), "n"(1));
  }
  template <uint32_t HB>
  static __device__ __forceinline__ void set(float* d, const uint32_t* a, uint32_t db) {
    asm volatile("{\n.reg .pred p;\n.reg .b64 db;\nsetp.ne.b32 p, %22, 0;\n"
      "mov.b64 db, {%20, %21};\n"
      "wgmma.mma_async.sync.aligned.m64n32k16.f32.bf16.bf16 {"
      "%0, %1, %2, %3, %4, %5, %6, %7, %8, %9, %10, %11, %12, %13, %14, %15"
      "}, {%16, %17, %18, %19}, db, p, 1, 1, 1;\n}\n"
      : "=f"(d[0]), "=f"(d[1]), "=f"(d[2]), "=f"(d[3]), "=f"(d[4]), "=f"(d[5]), "=f"(d[6]), "=f"(d[7]),
        "=f"(d[8]), "=f"(d[9]), "=f"(d[10]), "=f"(d[11]), "=f"(d[12]), "=f"(d[13]), "=f"(d[14]), "=f"(d[15])
      : "r"(a[0]), "r"(a[1]), "r"(a[2]), "r"(a[3]), "r"(db), "n"(HB), "n"(0));
  }
};
template <> struct WgRS<64> {
  template <uint32_t HB>
  static __device__ __forceinline__ void mma(float* d, const uint32_t* a, uint32_t db) {
    asm volatile("{\n.reg .pred p;\n.reg .b64 db;\nsetp.ne.b32 p, %38, 0;\n"
      "mov.b64 db, {%36, %37};\n"
      "wgmma.mma_async.sync.aligned.m64n64k16.f32.bf16.bf16 {"
      "%0, %1, %2, %3, %4, %5, %6, %7, %8, %9, %10, %11, %12, %13, %14, %15, "
      "%16, %17, %18, %19, %20, %21, %22, %23, %24, %25, %26, %27, %28, %29, %30, %31"
      "}, {%32, %33, %34, %35}, db, p, 1, 1, 1;\n}\n"
      : "+f"(d[0]), "+f"(d[1]), "+f"(d[2]), "+f"(d[3]), "+f"(d[4]), "+f"(d[5]), "+f"(d[6]), "+f"(d[7]),
        "+f"(d[8]), "+f"(d[9]), "+f"(d[10]), "+f"(d[11]), "+f"(d[12]), "+f"(d[13]), "+f"(d[14]), "+f"(d[15]),
        "+f"(d[16]), "+f"(d[17]), "+f"(d[18]), "+f"(d[19]), "+f"(d[20]), "+f"(d[21]), "+f"(d[22]), "+f"(d[23]),
        "+f"(d[24]), "+f"(d[25]), "+f"(d[26]), "+f"(d[27]), "+f"(d[28]), "+f"(d[29]), "+f"(d[30]), "+f"(d[31])
      : "r"(a[0]), "r"(a[1]), "r"(a[2]), "r"(a[3]), "r"(db), "n"(HB), "n"(1));
  }
  template <uint32_t HB>
  static __device__ __forceinline__ void set(float* d, const uint32_t* a, uint32_t db) {
    asm volatile("{\n.reg .pred p;\n.reg .b64 db;\nsetp.ne.b32 p, %38, 0;\n"
      "mov.b64 db, {%36, %37};\n"
      "wgmma.mma_async.sync.aligned.m64n64k16.f32.bf16.bf16 {"
      "%0, %1, %2, %3, %4, %5, %6, %7, %8, %9, %10, %11, %12, %13, %14, %15, "
      "%16, %17, %18, %19, %20, %21, %22, %23, %24, %25, %26, %27, %28, %29, %30, %31"
      "}, {%32, %33, %34, %35}, db, p, 1, 1, 1;\n}\n"
      : "=f"(d[0]), "=f"(d[1]), "=f"(d[2]), "=f"(d[3]), "=f"(d[4]), "=f"(d[5]), "=f"(d[6]), "=f"(d[7]),
        "=f"(d[8]), "=f"(d[9]), "=f"(d[10]), "=f"(d[11]), "=f"(d[12]), "=f"(d[13]), "=f"(d[14]), "=f"(d[15]),
        "=f"(d[16]), "=f"(d[17]), "=f"(d[18]), "=f"(d[19]), "=f"(d[20]), "=f"(d[21]), "=f"(d[22]), "=f"(d[23]),
        "=f"(d[24]), "=f"(d[25]), "=f"(d[26]), "=f"(d[27]), "=f"(d[28]), "=f"(d[29]), "=f"(d[30]), "=f"(d[31])
      : "r"(a[0]), "r"(a[1]), "r"(a[2]), "r"(a[3]), "r"(db), "n"(HB), "n"(0));
  }
};
template <> struct WgSST<48> {
  template <uint32_t HA, uint32_t HB>
  static __device__ __forceinline__ void mma(float* d, uint32_t da, uint32_t db, int sc) {
    asm volatile("{\n.reg .pred p;\n.reg .b64 da, db;\nsetp.ne.b32 p, %28, 0;\n"
      "mov.b64 da, {%24, %25};\nmov.b64 db, {%26, %27};\n"
      "wgmma.mma_async.sync.aligned.m64n48k16.f32.bf16.bf16 {"
      "%0, %1, %2, %3, %4, %5, %6, %7, %8, %9, %10, %11, %12, %13, %14, %15, "
      "%16, %17, %18, %19, %20, %21, %22, %23"
      "}, da, db, p, 1, 1, 0, 1;\n}\n"
      : "+f"(d[0]), "+f"(d[1]), "+f"(d[2]), "+f"(d[3]), "+f"(d[4]), "+f"(d[5]), "+f"(d[6]), "+f"(d[7]),
        "+f"(d[8]), "+f"(d[9]), "+f"(d[10]), "+f"(d[11]), "+f"(d[12]), "+f"(d[13]), "+f"(d[14]), "+f"(d[15]),
        "+f"(d[16]), "+f"(d[17]), "+f"(d[18]), "+f"(d[19]), "+f"(d[20]), "+f"(d[21]), "+f"(d[22]), "+f"(d[23])
      : "r"(da), "n"(HA), "r"(db), "n"(HB), "r"(sc));
  }
};
template <> struct WgSST<80> {
  template <uint32_t HA, uint32_t HB>
  static __device__ __forceinline__ void mma(float* d, uint32_t da, uint32_t db, int sc) {
    asm volatile("{\n.reg .pred p;\n.reg .b64 da, db;\nsetp.ne.b32 p, %44, 0;\n"
      "mov.b64 da, {%40, %41};\nmov.b64 db, {%42, %43};\n"
      "wgmma.mma_async.sync.aligned.m64n80k16.f32.bf16.bf16 {"
      "%0, %1, %2, %3, %4, %5, %6, %7, %8, %9, %10, %11, %12, %13, %14, %15, "
      "%16, %17, %18, %19, %20, %21, %22, %23, %24, %25, %26, %27, %28, %29, %30, %31, "
      "%32, %33, %34, %35, %36, %37, %38, %39"
      "}, da, db, p, 1, 1, 0, 1;\n}\n"
      : "+f"(d[0]), "+f"(d[1]), "+f"(d[2]), "+f"(d[3]), "+f"(d[4]), "+f"(d[5]), "+f"(d[6]), "+f"(d[7]),
        "+f"(d[8]), "+f"(d[9]), "+f"(d[10]), "+f"(d[11]), "+f"(d[12]), "+f"(d[13]), "+f"(d[14]), "+f"(d[15]),
        "+f"(d[16]), "+f"(d[17]), "+f"(d[18]), "+f"(d[19]), "+f"(d[20]), "+f"(d[21]), "+f"(d[22]), "+f"(d[23]),
        "+f"(d[24]), "+f"(d[25]), "+f"(d[26]), "+f"(d[27]), "+f"(d[28]), "+f"(d[29]), "+f"(d[30]), "+f"(d[31]),
        "+f"(d[32]), "+f"(d[33]), "+f"(d[34]), "+f"(d[35]), "+f"(d[36]), "+f"(d[37]), "+f"(d[38]), "+f"(d[39])
      : "r"(da), "n"(HA), "r"(db), "n"(HB), "r"(sc));
  }
};
template <> struct WgSST<192> {
  template <uint32_t HA, uint32_t HB>
  static __device__ __forceinline__ void mma(float* d, uint32_t da, uint32_t db, int sc) {
    asm volatile("{\n.reg .pred p;\n.reg .b64 da, db;\nsetp.ne.b32 p, %100, 0;\n"
      "mov.b64 da, {%96, %97};\nmov.b64 db, {%98, %99};\n"
      "wgmma.mma_async.sync.aligned.m64n192k16.f32.bf16.bf16 {"
      "%0, %1, %2, %3, %4, %5, %6, %7, %8, %9, %10, %11, %12, %13, %14, %15, "
      "%16, %17, %18, %19, %20, %21, %22, %23, %24, %25, %26, %27, %28, %29, %30, %31, "
      "%32, %33, %34, %35, %36, %37, %38, %39, %40, %41, %42, %43, %44, %45, %46, %47, "
      "%48, %49, %50, %51, %52, %53, %54, %55, %56, %57, %58, %59, %60, %61, %62, %63, "
      "%64, %65, %66, %67, %68, %69, %70, %71, %72, %73, %74, %75, %76, %77, %78, %79, "
      "%80, %81, %82, %83, %84, %85, %86, %87, %88, %89, %90, %91, %92, %93, %94, %95"
      "}, da, db, p, 1, 1, 0, 1;\n}\n"
      : "+f"(d[0]), "+f"(d[1]), "+f"(d[2]), "+f"(d[3]), "+f"(d[4]), "+f"(d[5]), "+f"(d[6]), "+f"(d[7]),
        "+f"(d[8]), "+f"(d[9]), "+f"(d[10]), "+f"(d[11]), "+f"(d[12]), "+f"(d[13]), "+f"(d[14]), "+f"(d[15]),
        "+f"(d[16]), "+f"(d[17]), "+f"(d[18]), "+f"(d[19]), "+f"(d[20]), "+f"(d[21]), "+f"(d[22]), "+f"(d[23]),
        "+f"(d[24]), "+f"(d[25]), "+f"(d[26]), "+f"(d[27]), "+f"(d[28]), "+f"(d[29]), "+f"(d[30]), "+f"(d[31]),
        "+f"(d[32]), "+f"(d[33]), "+f"(d[34]), "+f"(d[35]), "+f"(d[36]), "+f"(d[37]), "+f"(d[38]), "+f"(d[39]),
        "+f"(d[40]), "+f"(d[41]), "+f"(d[42]), "+f"(d[43]), "+f"(d[44]), "+f"(d[45]), "+f"(d[46]), "+f"(d[47]),
        "+f"(d[48]), "+f"(d[49]), "+f"(d[50]), "+f"(d[51]), "+f"(d[52]), "+f"(d[53]), "+f"(d[54]), "+f"(d[55]),
        "+f"(d[56]), "+f"(d[57]), "+f"(d[58]), "+f"(d[59]), "+f"(d[60]), "+f"(d[61]), "+f"(d[62]), "+f"(d[63]),
        "+f"(d[64]), "+f"(d[65]), "+f"(d[66]), "+f"(d[67]), "+f"(d[68]), "+f"(d[69]), "+f"(d[70]), "+f"(d[71]),
        "+f"(d[72]), "+f"(d[73]), "+f"(d[74]), "+f"(d[75]), "+f"(d[76]), "+f"(d[77]), "+f"(d[78]), "+f"(d[79]),
        "+f"(d[80]), "+f"(d[81]), "+f"(d[82]), "+f"(d[83]), "+f"(d[84]), "+f"(d[85]), "+f"(d[86]), "+f"(d[87]),
        "+f"(d[88]), "+f"(d[89]), "+f"(d[90]), "+f"(d[91]), "+f"(d[92]), "+f"(d[93]), "+f"(d[94]), "+f"(d[95])
      : "r"(da), "n"(HA), "r"(db), "n"(HB), "r"(sc));
  }
};

struct FftConst {
  uint32_t f[2][4], fi[4][4];
  uint32_t ta[2][2], tb[2][2];
};
__device__ __forceinline__ void cis(int m, float scale, float& c, float& s) {
  const float a = (float)m * (-6.283185307179586f * scale);
  c = __cosf(a);
  s = __sinf(a);
}
__device__ __forceinline__ void fft_tables(uint32_t (&v)[12], int tw) {
  const int row = tw >> 2, ch = tw & 3;
#pragma unroll
  for (int i = 0; i < 4; i++) {
    float c[2], s[2], x[2];
#pragma unroll
    for (int e = 0; e < 2; e++) {
      cis((((32 * (8 * ch + 2 * i + e) + 15) * (4 * row - 63) + 2048) & 4095) - 2048, 1.f / 4096, c[e], s[e]);
      float gc, gs;
      cis((((row & 15) * (8 * (ch & 1) + 2 * i + e) + 8) & 15) - 8, 1.f / 16, gc, gs);
      x[e] = (row >> 4) == (ch >> 1) ? gc : (ch >> 1) ? gs : -gs;
    }
    v[i] = pack2(c[0] * 0.125f, c[1] * 0.125f);
    v[4 + i] = pack2(s[0] * 0.125f, s[1] * 0.125f);
    v[8 + i] = pack2(x[0], x[1]);
  }
#pragma unroll
  for (int i = 0; i < 12; i++) asm volatile("" : "+r"(v[i]));
}
__device__ __forceinline__ void fft_tables_store(const uint32_t (&v)[12], uint32_t sb, int tw) {
  const int row = tw >> 2;
  const uint32_t x = ((tw ^ (row >> 1)) & 3) << 4, a = sb + OFF_FT + (16 * (row >> 3) + (row & 7)) * 64 + x;
  sts128(a, v[0], v[1], v[2], v[3]);
  sts128(a + 512, v[4], v[5], v[6], v[7]);
  sts128(sb + OFF_GT + row * 64 + x, v[8], v[9], v[10], v[11]);
}
__device__ __forceinline__ void fft_twiddles(uint32_t (&v)[2], int tw) {
  float a[2], s[2];
#pragma unroll
  for (int i = 0; i < 2; i++) {
    float c;
    cis((2 * (2 * (tw & 3) + i) - 15) * (4 * (tw >> 2) - 63), 1.f / 4096, c, s[i]);
    a[i] = __fdividef(-s[i], 1.f + c);
  }
  v[0] = pack2(a[0], a[1]);
  v[1] = pack2(s[0], s[1]);
  asm volatile("" : "+r"(v[0]), "+r"(v[1]));
}
__device__ __forceinline__ void fft_matrices(FftConst& k, uint32_t sb, int w, int lane) {
  const uint32_t x = (lane >> 1) & 3;
  const uint2 t0 = lds64(sb + OFF_TT + 256 * w + 8 * lane), t1 = lds64(sb + OFF_TT + 256 * w + 8 * (lane ^ 3));
  k.ta[0][0] = t0.x;
  k.tb[0][0] = t0.y;
  k.ta[1][1] = __byte_perm(t1.x, 0, 0x1032);
  k.tb[1][1] = __byte_perm(t1.y, 0, 0x1032);
#pragma unroll
  for (int j = 0; j < 2; j++) {
    k.ta[1 - j][j] = k.ta[j][j] ^ 0x80008000u;
    k.tb[1 - j][j] = k.tb[j][j] ^ 0x80008000u;
    asm volatile("" : "+r"(k.ta[0][j]), "+r"(k.tb[0][j]), "+r"(k.ta[1][j]), "+r"(k.tb[1][j]));
  }
#pragma unroll
  for (int i = 0; i < 2; i++) {
    ldsm4(k.f[i], sb + OFF_FT + (16 * w + (lane & 15)) * 64 + (((2 * i + (lane >> 4)) ^ x) << 4));
    ldsm4t(k.fi[i], sb + OFF_FT + (32 * i + lane) * 64 + ((w ^ x) << 4));
#pragma unroll
    for (int j = 0; j < 4; j++) {
      k.fi[2 + i][j] = (j & 1) ? k.fi[i][j - 1] ^ 0x80008000u : k.fi[i][j + 1];
      asm volatile("" : "+r"(k.fi[2 + i][j]));
    }
  }
}
__device__ __forceinline__ void rot(uint32_t& x, uint32_t& y, uint32_t a, uint32_t b) {
  x = bfma(a, y, x);
  y = bfma(b, x, y);
  x = bfma(a, y, x);
}
__device__ __forceinline__ void twiddle_fwd(uint32_t (&a)[4][4], float* d, const FftConst& k) {
#pragma unroll
  for (int q = 0; q < 4; q++)
#pragma unroll
    for (int j = 0; j < 2; j++) {
      const float* x = d + 8 * q + 4 * j;
      uint32_t re = pack2(x[0], x[1]), im = pack2(x[2], x[3]);
      rot(re, im, k.ta[0][j], k.tb[0][j]);
      a[q & 2][2 * j + (q & 1)] = re;
      a[(q & 2) + 1][2 * j + (q & 1)] = im;
    }
}
__device__ __forceinline__ void g_step(float* d, const uint32_t (&a)[4][4], uint32_t dre, uint32_t dim) {
  WgRS<32>::set<HI_SW64>(d, a[0], dre);
  WgRS<32>::set<HI_SW64>(d + 16, a[2], dre);
  WgRS<32>::mma<HI_SW64>(d, a[1], dim);
  WgRS<32>::mma<HI_SW64>(d + 16, a[3], dim);
  wg_commit();
}

__device__ __forceinline__ void conv_channel(const FftConst& k, uint32_t sb, int c, int wg, int w, int lane) {
  const uint32_t cb = sb + off_ch(c), bars = sb + OFF_BAR;
  const uint32_t du = desc_lo(cb, 1024), dg = desc_lo(sb + OFF_GT, 16), dz = desc_lo(cb + U_BYTES, 16);
  float U[32], H[32];
  uint32_t a[4][4], e[4][4];
  const float dv = __uint_as_float(lds32(sb + OFF_D + 4 * c));
  wg_fence();
  WgRS<64>::set<HI_SW32>(H, k.f[0], du + 256);
  WgRS<64>::mma<HI_SW32>(H, k.f[1], du + 256 + 32);
  wg_commit();
  wg_wait<0>();
  pin<32>(H);
  twiddle_fwd(a, H, k);
  if (ATT_GATE) mbar_wait(bars + 8 * (ATT_GATE == 1 ? B_ATTN : B_ATT2), 0);
  mbar_wait(bars + 8 * (B_U + (c < 3 ? c : 3)), 0);
  TSM(w == 0 && c < 3, 7 + wg);
  wg_fence();
  WgRS<64>::set<HI_SW32>(U, k.f[0], du);
  WgRS<64>::mma<HI_SW32>(U, k.f[1], du + 32);
  wg_commit();
  g_step(H, a, dg, dg + 64);
  wg_wait<1>();
  pin<32>(U);
  twiddle_fwd(e, U, k);
  wg_fence();
  g_step(U, e, dg, dg + 64);
  wg_wait<0>();
  pin<32>(U);
  pin<32>(H);
#pragma unroll
  for (int j = 0; j < 2; j++) {
    float pr[4][2], pi[4][2];
#pragma unroll
    for (int x = 0; x < 2; x++) {
      H[4 * j + x] += dv;
#pragma unroll
      for (int m = 0; m < 4; m++) {
#pragma unroll
        for (int q = 0; q <= m; q++) {
          const int ih = 16 * (q >> 1) + 2 * (q & 1) + 4 * j + x, iu = 16 * ((m - q) >> 1) + 2 * ((m - q) & 1) + 4 * j + x;
          pr[m][x] = q ? fmaf(H[ih], U[iu], pr[m][x]) : H[ih] * U[iu];
          pi[m][x] = q ? fmaf(H[ih], U[iu + 8], pi[m][x]) : H[ih] * U[iu + 8];
          pr[m][x] = fmaf(-H[ih + 8], U[iu + 8], pr[m][x]);
          pi[m][x] = fmaf(H[ih + 8], U[iu], pi[m][x]);
        }
      }
    }
#pragma unroll
    for (int m = 0; m < 4; m++) {
      a[m & 2][2 * j + (m & 1)] = pack2(pr[m][0], pr[m][1]);
      a[(m & 2) + 1][2 * j + (m & 1)] = pack2(pi[m][0], pi[m][1]);
    }
  }
  wg_fence();
  g_step(U, a, dg + 64, dg);
  const uint32_t za = cb + U_BYTES + (8 * w + (lane & 7)) * 128 + (((lane >> 3) ^ (lane & 7)) << 4);
  const uint32_t ya = cb + (lane >> 4) * 1024 + (8 * w + (lane & 7)) * 32 + ((((lane >> 3) ^ (lane >> 2)) & 1) << 4);
  wg_sync(1 + wg);
  wg_wait<0>();
  pin<32>(U);
  TSIF(w == 0, 80 + c);
#pragma unroll
  for (int p = 0; p < 2; p++) {
#pragma unroll
    for (int i = 0; i < 4; i++) {
      const int j = i & 1;
      const float* x = U + 16 * p + 4 * j + (i & 2);
      e[p][i] = pack2(x[8], x[9]);
      e[2 + p][i] = pack2(x[0], x[1]);
      rot(e[p][i], e[2 + p][i], k.ta[1][j], k.tb[1][j]);
    }
    stsm4(za ^ (64 * p), e[p]);
    stsm4((za ^ (64 * p)) + 4096, e[2 + p]);
  }
  fence_async_smem();
  wg_sync(1 + wg);
  wg_fence();
  WgRS<64>::set<HI_SW128>(H, k.fi[0], dz);
#pragma unroll
  for (int ks = 1; ks < 4; ks++) WgRS<64>::mma<HI_SW128>(H, k.fi[ks], dz + 128 * ks);
  wg_commit();
  if (WO_FAST) mbar_wait(bars + 8 * B_ATTN, 0);
  wg_wait<0>();
  pin<32>(H);
  TSIF(w == 0, 88 + c);
#pragma unroll
  for (int j = 0; j < 8; j++)
    a[j >> 2][j & 3] = j < 2 ? pack2(H[4 * j], H[4 * j + 1]) : pack2(H[4 * j] + H[4 * j - 6], H[4 * j + 1] + H[4 * j - 5]);
  stsm4(ya, a[0]);
  stsm4(ya + 2048, a[1]);
  fence_async_smem();
  __syncwarp();
}

__device__ __forceinline__ void prep_slab(uint4* res, const uint2* sw, uint32_t sb, int slab, int w, int lane) {
  const int t = lane & 3, tp = (lane & 7) >> 1, pos = 8 * tp + 2 * (((lane >> 3) + tp) & 3) + (lane & 1);
  const uint32_t base = sb + OFF_KVS + slab * KVS_BYTES + pos * 128;
  uint32_t kk[2][4][4], vv[2][4];
  mbar_wait(sb + OFF_BAR + 8 * (B_KV + slab), 0);
#pragma unroll
  for (int h = 0; h < 2; h++) {
#pragma unroll
    for (int j = 0; j < 4; j++) {
      const uint32_t a = base + 128 * j;
      ldsm4t(kk[h][j], a + (((w + 4 * h) ^ ((a >> 7) & 7)) << 4));
    }
    const uint32_t a = base + KVS_V;
    ldsm4t(vv[h], a + (((w + 4 * h) ^ ((a >> 7) & 7)) << 4));
  }
#pragma unroll
  for (int h = 0; h < 2; h++) {
    uint32_t (&k)[4][4] = kk[h];
    uint32_t (&v)[4] = vv[h];
    const uint32_t w0 = __byte_perm(sw[h].x, 0, 0x1010), w1 = __byte_perm(sw[h].x, 0, 0x3232);
    const uint32_t w2 = __byte_perm(sw[h].y, 0, 0x1010), w3 = __byte_perm(sw[h].y, 0, 0x3232);
#pragma unroll
    for (int m = 0; m < 4; m++)
      v[m] = bmul(badd(badd(badd(bmul(k[0][m], w3), bmul(k[1][m], w2)), bmul(k[2][m], w1)), bmul(k[3][m], w0)), v[m]);
    uint32_t a[4];
#pragma unroll
    for (int m = 0; m < 4; m++) a[m] = (t & 1) ? v[(m + 3) & 3] : v[m];
    res[h] = (t & 2) ? make_uint4(a[2], a[3], a[0], a[1]) : make_uint4(a[0], a[1], a[2], a[3]);
  }
}

__device__ __forceinline__ void prep_gate(const Params& p, uint32_t sb, int b, int w, int lane) {
  uint2 gw[5], x[4][5];
#pragma unroll
  for (int j = 0; j < 5; j++) gw[j] = ldg64(reinterpret_cast<const uint2*>(p.gate_w) + lane + 32 * j);
#pragma unroll
  for (int i = 0; i < 4; i++)
#pragma unroll
    for (int j = 0; j < 5; j++)
      x[i][j] = ldg64(reinterpret_cast<const uint2*>(p.q) + (16 * b + 4 * w + i) * (DIM / 4) + lane + 32 * j);
  float s[4];
#pragma unroll
  for (int i = 0; i < 4; i++) {
    s[i] = 0.f;
#pragma unroll
    for (int j = 0; j < 5; j++) {
      const uint32_t m0 = bmul(x[i][j].x, gw[j].x), m1 = bmul(x[i][j].y, gw[j].y);
      s[i] += (bf_lo(m0) + bf_hi(m0)) + (bf_lo(m1) + bf_hi(m1));
    }
  }
  const bool h = lane & 16, q = lane & 8;
  const float a = (h ? s[2] : s[0]) + __shfl_xor_sync(0xffffffffu, h ? s[0] : s[2], 16);
  const float c = (h ? s[3] : s[1]) + __shfl_xor_sync(0xffffffffu, h ? s[1] : s[3], 16);
  float z = (q ? c : a) + __shfl_xor_sync(0xffffffffu, q ? a : c, 8);
#pragma unroll
  for (int o = 4; o > 0; o >>= 1) z += __shfl_xor_sync(0xffffffffu, z, o);
  z = bf_lo(pack2(z, 0.f));
  z = bf_lo(pack2(__fdividef(1.f, 1.f + __expf(-z)), 0.f));
  if (G_TMA) {
    mbar_wait(sb + OFF_BAR + 8 * B_S3, 0);
    if ((lane & 7) == 0) asm volatile("st.shared.f32 [%0], %1;" ::"r"(sb + OFF_GATE + 64 * (b & 7) + 16 * w + (lane >> 1)), "f"(z) : "memory");
    fence_async_smem();
  } else if ((lane & 7) == 0) {
    g_gate[16 * b + 4 * w + (lane >> 3)] = z;
  }
}

__device__ __forceinline__ uint32_t bmax(uint32_t a, uint32_t b) {
  uint32_t d;
  asm("max.bf16x2 %0, %1, %2;" : "=r"(d) : "r"(a), "r"(b));
  return d;
}
__device__ __forceinline__ void softmax_two(const float (&l)[2][2], uint32_t& p0, uint32_t& p1) {
  constexpr float kScale = 0.22360679774997896f, kLog2e = 1.4426950408889634f;
  const uint32_t r0 = pack2(l[0][0], l[1][0]), r1 = pack2(l[0][1], l[1][1]);
  const uint32_t x0 = pack2(bf_lo(r0) * kScale, bf_hi(r0) * kScale), x1 = pack2(bf_lo(r1) * kScale, bf_hi(r1) * kScale);
  uint32_t m = bmax(x0, x1);
  m = bmax(m, __shfl_xor_sync(0xffffffffu, m, 1));
  m = bmax(m, __shfl_xor_sync(0xffffffffu, m, 2));
  const float m0 = bf_lo(m) * kLog2e, m1 = bf_hi(m) * kLog2e;
  p0 = pack2(ex2(bf_lo(x0) * kLog2e - m0), ex2(bf_lo(x1) * kLog2e - m0));
  p1 = pack2(ex2(bf_hi(x0) * kLog2e - m1), ex2(bf_hi(x1) * kLog2e - m1));
}

__device__ __forceinline__ void halo_read(uint32_t (&kpv)[10], uint32_t (&vpv)[10], uint32_t (&tg)[7], const uint4* hp) {
#pragma unroll
  for (int j = 0; j < 7; j++) {
    uint32_t x0, x1, x2;
    asm volatile("ld.relaxed.gpu.global.v4.u32 {%0, %1, %2, %3}, [%4];"
                 : "=r"(x0), "=r"(x1), "=r"(x2), "=r"(tg[j]) : "l"(hp + 32 * j) : "memory");
    if (j < 4) kpv[3 * j] = x0; else vpv[3 * j - 10] = x0;
    if (j < 3) kpv[3 * j + 1] = x1; else vpv[3 * j - 9] = x1;
    if (j < 3) kpv[3 * j + 2] = x2; else if (j < 6) vpv[3 * j - 8] = x2;
  }
}

template <int ROT>
__device__ __forceinline__ void pack_qkv(const float* acc, uint32_t (&qlo)[10], uint32_t (&qhi)[10], uint32_t (&klo)[10],
                                         uint32_t (&khi)[10], uint32_t (&vlo)[10], uint32_t (&vhi)[10]) {
#pragma unroll
  for (int j = 0; j < 10; j++) {
    const int x = (j + ROT) % 10, tq = x < 8 ? x : 16 + x, tk = x < 8 ? 8 + x : 18 + x, tv = x < 8 ? 16 + x : 20 + x;
    khi[j] = pack2(acc[4 * tk + 2], acc[4 * tk + 3]);
    vhi[j] = movm(pack2(acc[4 * tv + 2], acc[4 * tv + 3]));
    qlo[j] = pack2(acc[4 * tq], acc[4 * tq + 1]);
    qhi[j] = pack2(acc[4 * tq + 2], acc[4 * tq + 3]);
    klo[j] = pack2(acc[4 * tk], acc[4 * tk + 1]);
    vlo[j] = pack2(acc[4 * tv], acc[4 * tv + 1]);
    asm volatile("" : "+r"(khi[j]), "+r"(qlo[j]), "+r"(qhi[j]), "+r"(klo[j]), "+r"(vlo[j]));
  }
}

template <int ROT> __device__ __forceinline__ void halo_send(const float* acc, uint4* ho, uint32_t tag) {
#pragma unroll
  for (int j = 0; j < 7; j++) {
    uint32_t x[3];
#pragma unroll
    for (int e = 0; e < 3; e++) {
      const int i = 3 * j + e, y = (i % 10 + ROT) % 10, tk = y < 8 ? 8 + y : 18 + y, tv = y < 8 ? 16 + y : 20 + y;
      x[e] = i < 10 ? pack2(acc[4 * tk + 2], acc[4 * tk + 3]) : i < 20 ? movm(pack2(acc[4 * tv + 2], acc[4 * tv + 3])) : 0u;
    }
    asm volatile("st.relaxed.gpu.global.v4.u32 [%0], {%1, %2, %3, %4};" ::"l"(ho + 32 * j), "r"(x[0]), "r"(x[1]), "r"(x[2]), "r"(tag) : "memory");
  }
}

__device__ __forceinline__ void attention(float* acc, uint32_t sb, int b, int par, int w, int lane, uint32_t tag, uint32_t zero) {
  const int g = lane >> 2, t = lane & 3;
  uint32_t klo[10], khi[10], vlo[10], vhi[10], qlo[10], qhi[10], kpv[10], vpv[10];
  if (HALO_FIRST && w == 3 && b < NCTA - 8) {
    uint4* ho = g_halo + (b * 2 + par) * 224 + lane;
    if (tail_first(b & 7)) halo_send<8>(acc, ho, tag);
    else halo_send<0>(acc, ho, tag);
    TSIF(par == 0, 76);
    pin<120>(acc);
  }
  if (tail_first(b & 7)) pack_qkv<8>(acc, qlo, qhi, klo, khi, vlo, vhi);
  else pack_qkv<0>(acc, qlo, qhi, klo, khi, vlo, vhi);
  const uint32_t xa = sb + OFF_KVX + (par * 3) * 2560 + lane * 16;
  if (w < 3) {
    sts128(xa + w * 2560, khi[0], khi[1], khi[2], khi[3]);
    sts128(xa + w * 2560 + 512, khi[4], khi[5], khi[6], khi[7]);
    sts128(xa + w * 2560 + 1024, khi[8], khi[9], vhi[0], vhi[1]);
    sts128(xa + w * 2560 + 1536, vhi[2], vhi[3], vhi[4], vhi[5]);
    sts128(xa + w * 2560 + 2048, vhi[6], vhi[7], vhi[8], vhi[9]);
  } else if (!HALO_FIRST && b < NCTA - 8) {
    uint4* ho = g_halo + (b * 2 + par) * 224 + lane;
#pragma unroll
    for (int j = 0; j < 7; j++) {
      const uint32_t x0 = j < 4 ? khi[3 * j] : vhi[3 * j - 10], x1 = j < 3 ? khi[3 * j + 1] : vhi[3 * j - 9];
      const uint32_t x2 = j < 3 ? khi[3 * j + 2] : j < 6 ? vhi[3 * j - 8] : 0u;
      asm volatile("st.relaxed.gpu.global.v4.u32 [%0], {%1, %2, %3, %4};" ::"l"(ho + 32 * j), "r"(x0), "r"(x1), "r"(x2), "r"(tag) : "memory");
    }
  }
  TSIF(par == 0 && w == 1, 64);
  TSIF(par == 0 && w == 3 && !HALO_FIRST, 76);
#pragma unroll
  for (int j = 0; j < 10; j++) vlo[j] = movm(vlo[j]);
  const bool far0 = 2 * t > g, far1 = 2 * t + 1 > g;
  const uint32_t mfar = (far0 ? 0x0000FFFFu : 0u) | (far1 ? 0xFFFF0000u : 0u);
  float slo[4][2], shi[4][2], lg[2][2];
  uint32_t phi[4], plo[4], qml[4], qmh[4];
#pragma unroll
  for (int h = 0; h < 4; h++) {
    const int f = h == 0 ? 0 : h == 1 ? 3 : h == 2 ? 5 : 8, hf = h < 2 ? 2 : 7;
    const bool mine = (h & 1) ? t >= 2 : t < 2;
    qml[h] = mine ? qlo[hf] : 0u;
    qmh[h] = mine ? qhi[hf] : 0u;
    float a[4] = {0.f, 0.f, 0.f, 0.f}, c[4] = {0.f, 0.f, 0.f, 0.f};
    mma16816(a, qlo[f], qhi[f], qlo[f + 1], qhi[f + 1], klo[f], klo[f + 1]);
    mma16816(c, qlo[f], qhi[f], qlo[f + 1], qhi[f + 1], khi[f], khi[f + 1]);
    mma1688(a, qml[h], qmh[h], klo[hf]);
    mma1688(c, qml[h], qmh[h], khi[hf]);
    slo[h][0] = a[0];
    slo[h][1] = a[1];
    shi[h][0] = lg[h & 1][0] = far0 ? a[2] : c[2];
    shi[h][1] = lg[h & 1][1] = far1 ? a[3] : c[3];
    if (!ATT_MERGE && (h & 1)) softmax_two(lg, phi[h - 1], phi[h]);
  }
  TSIF(par == 0 && w == 1, 65);
  if (ATT_GATE == 3 && lane == 0) mbar_arrive(sb + OFF_BAR + 8 * B_ATT2 + (phi[3] & zero));
  wg_sync(1 + par);
  TSIF(par == 0 && w == 1, 66);
  const bool nohist = (w == 0) && (b < 8);
  const uint4* hp = g_halo + ((b - 8) * 2 + par) * 224 + lane;
  uint32_t tg[7];
  if (w > 0) {
    const uint4 v0 = lds128(xa + (w - 1) * 2560), v1 = lds128(xa + (w - 1) * 2560 + 512), v2 = lds128(xa + (w - 1) * 2560 + 1024);
    const uint4 v3 = lds128(xa + (w - 1) * 2560 + 1536), v4 = lds128(xa + (w - 1) * 2560 + 2048);
    kpv[0] = v0.x; kpv[1] = v0.y; kpv[2] = v0.z; kpv[3] = v0.w; kpv[4] = v1.x; kpv[5] = v1.y; kpv[6] = v1.z; kpv[7] = v1.w;
    kpv[8] = v2.x; kpv[9] = v2.y; vpv[0] = v2.z; vpv[1] = v2.w; vpv[2] = v3.x; vpv[3] = v3.y; vpv[4] = v3.z; vpv[5] = v3.w;
    vpv[6] = v4.x; vpv[7] = v4.y; vpv[8] = v4.z; vpv[9] = v4.w;
  } else if (nohist) {
#pragma unroll
    for (int j = 0; j < 10; j++) kpv[j] = vpv[j] = 0u;
  } else {
    TSIF(par == 0, 77);
    halo_read(kpv, vpv, tg, hp);
  }
  if (w == 0 && !nohist) {
    int spins = 0;
    while (true) {
      bool ok = true;
#pragma unroll
      for (int j = 0; j < 7; j++) ok = ok && tg[j] == tag;
      if (__all_sync(0xffffffffu, ok) || ++spins > SPIN_LIMIT) break;
      halo_read(kpv, vpv, tg, hp);
    }
    TSIF(par == 0, 79);
  }
#pragma unroll
  for (int h = 0; h < 4; h++) {
    const int f = h == 0 ? 0 : h == 1 ? 3 : h == 2 ? 5 : 8, hf = h < 2 ? 2 : 7;
    float a[4] = {0.f, 0.f, 0.f, 0.f};
    mma16816(a, qlo[f], qhi[f], qlo[f + 1], qhi[f + 1], kpv[f], kpv[f + 1]);
    mma1688(a, qml[h], qmh[h], kpv[hf]);
    const float ninf = __int_as_float(0xff800000);
    lg[h & 1][0] = far0 ? (nohist ? ninf : a[0]) : slo[h][0];
    lg[h & 1][1] = far1 ? (nohist ? ninf : a[1]) : slo[h][1];
    if (h & 1) {
      softmax_two(lg, plo[h - 1], plo[h]);
      if (ATT_MERGE) {
        const float lh[2][2] = {{shi[h - 1][0], shi[h - 1][1]}, {shi[h][0], shi[h][1]}};
        softmax_two(lh, phi[h - 1], phi[h]);
      }
    }
  }
  TSIF(par == 0 && w <= 1, 67 + w);
  if (ATT_GATE == 2 && lane == 0) mbar_arrive(sb + OFF_BAR + 8 * B_ATT2 + (plo[3] & zero));
  uint32_t ov[20];
#pragma unroll
  for (int hp = 0; hp < 2; hp++) {
    const int hf = hp ? 7 : 2;
    float sh[4] = {0.f, 0.f, 0.f, 0.f}, i0 = 0.f, i1 = 0.f;
#pragma unroll
    for (int e = 0; e < 2; e++) {
      const int h = 2 * hp + e, f = h == 0 ? 0 : h == 1 ? 3 : h == 2 ? 5 : 8;
      const uint32_t a0 = plo[h] & mfar, a2 = plo[h] & ~mfar, a3 = phi[h] & mfar, c1 = phi[h] & ~mfar;
      float sum[4] = {0.f, 0.f, 0.f, 0.f};
      mma1688(sum, plo[h], phi[h], 0x3F803F80u);
      const float r0 = rcp(sum[0]), r1 = rcp(sum[2]);
#pragma unroll
      for (int j = f; j < f + 2; j++) {
        float o[4] = {0.f, 0.f, 0.f, 0.f};
        mma16816(o, a0, 0u, a2, a3, vpv[j], vlo[j]);
        mma1688(o, 0u, c1, vhi[j]);
        ov[2 * j] = pack2(o[0] * r0, o[1] * r0);
        ov[2 * j + 1] = pack2(o[2] * r1, o[3] * r1);
      }
      const bool mine = e ? g >= 4 : g < 4;
      mma16816(sh, a0, 0u, a2, a3, mine ? vpv[hf] : 0u, mine ? vlo[hf] : 0u);
      mma1688(sh, 0u, c1, mine ? vhi[hf] : 0u);
      if (e == 0 || t >= 2) {
        i0 = r0;
        i1 = r1;
      }
    }
    ov[2 * hf] = pack2(sh[0] * i0, sh[1] * i0);
    ov[2 * hf + 1] = pack2(sh[2] * i1, sh[3] * i1);
  }
  if (ATT_GATE == 4 && lane == 0) mbar_arrive(sb + OFF_BAR + 8 * B_ATT2 + (ov[19] & zero));
  TS(32 + 4 * par + w);
  mbar_wait(sb + OFF_BAR + 8 * B_P1, 0);
  const uint32_t oa = sb + OFF_OA + (lane >> 4) * 2048 + (32 * w + 2 * (lane & 15) + par) * 16;
#pragma unroll
  for (int j = 0; j < 5; j++) stsm4(oa + 4096 * j, ov + 4 * j);
  TSIF(par == 0 && w == 0, 120);
  fence_async_smem();
  TSIF(par == 0 && w == 0, 121);
  __syncwarp();
  if (lane == 0) mbar_arrive(sb + OFF_BAR + 8 * B_ATTN);
  TSM(w == 0 || w == 2, 122 + par + (w == 2 ? 3 : 0));
}

struct Maps {
  CUtensorMap x, wm, wt, k, v, y, wo, qm, qt, om, ot, u;
};

__device__ __forceinline__ void load_stage(uint32_t sb, int kb, int b, const Maps& m) {
  const uint32_t st = sb + (kb & 3) * STAGE_BYTES, bar = sb + OFF_BAR + 8 * (B_FULL1 + (kb & 3));
  const int r = b >> 3, hg = b & 7, slab = kb - KV_KB;
  const bool kv = slab >= 0 && slab < 5;
  const uint32_t kbar = sb + OFF_BAR + 8 * (B_KV + slab), dst = sb + OFF_KVS + slab * KVS_BYTES;
  mbar_expect_tx(bar, STAGE_BYTES);
  if (kv) mbar_expect_tx(kbar, KVS_BYTES);
  tma_3d(st, &m.x, 64 * kb, 64 * r, 0, bar);
  if (kv && KV_MIX) tma_3d(dst, &m.k, 0, 32 * (b >> 1) - 3, 2 * slab + (b & 1), kbar);
  tma_3d(st + ST_W, &m.wm, 80 * hg + (tail_first(hg) ? 16 : 0), 64 * kb, 0, bar);
  if (kv && KV_MIX) tma_3d(dst + KVS_V, &m.v, 0, 32 * (b >> 1), 2 * slab + (b & 1), kbar);
  tma_3d(st + ST_WT, &m.wt, 80 * hg + (tail_first(hg) ? 0 : 64), 64 * kb, 0, bar);
  if (kv && !KV_MIX) tma_3d(dst, &m.k, 0, 32 * (b >> 1) - 3, 2 * slab + (b & 1), kbar);
  if (kv && !KV_MIX) tma_3d(dst + KVS_V, &m.v, 0, 32 * (b >> 1), 2 * slab + (b & 1), kbar);
}

__global__ void __launch_bounds__(NTHR, 1) fused_kernel(const __grid_constant__ Maps m, const Params p) {
  extern __shared__ __align__(1024) uint8_t smem[];
  const uint32_t sb = (uint32_t)__cvta_generic_to_shared(smem);
  const uint32_t bars = sb + OFF_BAR;
  const int tid = threadIdx.x, lane = tid & 31;
  int b = blockIdx.x;
  if (BMAP == 1) b = (((b & 63) >> 3) * 2 + (b & 1)) * 8 + (((b < 64 ? 0x6521 : 0x7430) >> (4 * ((b >> 1) & 3))) & 7);
  if (BMAP == 2) b = ((b & 63) >> 2) * 8 + (((b < 64 ? 0x6521 : 0x7430) >> (4 * (b & 3))) & 7);
  if (BMAP == 3) b = (((b & 63) >> 3) * 2 + (b & 1)) * 8 + (((b < 64 ? 0x7430 : 0x6521) >> (4 * ((b >> 1) & 3))) & 7);
  if (BMAP == 4) b = (((b >> 4) * 2 + (b & 1)) * 8) + ((b >> 1) & 7);
  if (BMAP == 5) b = 127 - b;
  const int r = b >> 3, hg = b & 7;

  if (tid == T_ISSUE) {
    TSM(true, 0);
#pragma unroll
    for (int i = 0; i < 4; i++) mbar_init(bars + 8 * (B_FULL1 + i), 1);
#pragma unroll
    for (int i = 0; i < 3; i++) mbar_init(bars + 8 * (B_KV + i), 1);
    fence_async_smem();
#pragma unroll 1
    for (int kb = 0; kb <= PRE2; kb++) load_stage(sb, kb, b, m);
  } else if (tid >= T_PF && tid < T_PF + 12) {
    tm_prefetch(&m.x + (tid - T_PF));
  } else if (tid == T_INIT) {
#pragma unroll
    for (int i = 0; i < 4; i++) mbar_init(bars + 8 * (B_EMPTY1 + i), 8);
#pragma unroll
    for (int i = 0; i < 8; i++) mbar_init(bars + 8 * (B_FULL2 + i), 1);
#pragma unroll
    for (int i = 0; i < 4; i++) mbar_init(bars + 8 * (B_EMPTY2 + i), 8);
#pragma unroll
    for (int i = 0; i < 4; i++) mbar_init(bars + 8 * (B_U + i), 1);
    mbar_init(bars + 8 * B_HA, 4);
    mbar_init(bars + 8 * B_GATE, 4);
    mbar_init(bars + 8 * B_HB, 1);
    mbar_init(bars + 8 * B_KVD, 4);
    mbar_init(bars + 8 * B_QF, 1);
    mbar_init(bars + 8 * B_ATTN, 8);
    mbar_init(bars + 8 * B_ATT2, 8);
    mbar_init(bars + 8 * B_P1, 8);
    mbar_init(bars + 8 * B_C34, 1);
    mbar_init(bars + 8 * B_YRB, 1);
#pragma unroll
    for (int i = 0; i < 5; i++) mbar_init(bars + 8 * (B_YST + i), 4);
#pragma unroll
    for (int i = 0; i < 5; i++) mbar_init(bars + 8 * (B_US + i), U_TMA ? 4 : 1);
    mbar_init(bars + 8 * B_YSIG, 1);
    mbar_init(bars + 8 * B_YFULL, 1);
    mbar_init(bars + 8 * B_EPOCH, 1);
    mbar_init(bars + 8 * B_PREP, 4);
    mbar_init(bars + 8 * B_USIG, 1);
    mbar_init(bars + 8 * B_WST, 1);
#pragma unroll
    for (int i = 3; i < 5; i++) mbar_init(bars + 8 * (B_KV + i), 1);
    mbar_init(bars + 8 * B_E3, 8);
    mbar_init(bars + 8 * B_LAST, 1);
    mbar_init(bars + 8 * B_OSIG, 1);
    mbar_init(bars + 8 * B_WOP, 1);
    fence_async_smem();
  }
  const int warp = __shfl_sync(0xffffffffu, tid >> 5, 0), wg = warp >> 2, w = warp & 3;
  __syncthreads();

  if (wg == 3) {
    asm volatile("setmaxnreg.dec.sync.aligned.u32 56;");
    if (w == 0) {
      if (lane == 0) {
#pragma unroll 1
        for (int kb = 1 + PRE2; kb < 10; kb++) {
          if (kb >= 4) mbar_wait(bars + 8 * (kb == 7 ? B_E3 : B_EMPTY1 + (kb & 3)), (kb >> 3) & 1);
          TSIF(kb >= 4, 44 + kb);
          load_stage(sb, kb, b, m);
          TSIF(kb == 3, 60);
          if (kb == TRIG_KB) mbar_arrive(bars + 8 * B_LAST);
        }
        mbar_wait(bars + 8 * B_WOP, 0);
        mbar_wait(bars + 8 * WL_TRIG, 0);
        mbar_wait(bars + 8 * B_EPOCH, 0);
        flag_wait(g_cnt + C_W + 32 * hg, (lds32(sb + OFF_EPOCH) + 1) * 16);
        TS(30);
#pragma unroll 1
        for (int j = 0; j < 8; j++) {
          if (j >= 6) mbar_wait(bars + 8 * (B_EMPTY2 + j - 6), 0);
          if (j == 4) mbar_wait(bars + 8 * B_ATTN, 0);
          TSIF(j >= 6, 100 + j);
          if (RF_GATE && j == 6) mbar_wait(bars + 8 * B_YSIG, 0);
          mbar_expect_tx(bars + 8 * (B_FULL2 + j), j == 0 ? WO_BYTES : j == 5 ? O_BYTES + WO_BYTES + 512 : O_BYTES + WO_BYTES);
          bulk_load(sb + off_w(j), g_WO + (hg * 8 + step_src(hg, j)) * 800, WO_BYTES, bars + 8 * (B_FULL2 + j));
        }
        mbar_wait(bars + 8 * (B_EMPTY2 + Q_SLOT), 0);
        mbar_expect_tx(bars + 8 * B_QF, O_BYTES);
        tma_2d(sb + OFF_QS, &m.qm, 80 * hg, 128 * r, bars + 8 * B_QF);
        if (!QBOX) tma_2d(sb + OFF_QT, &m.qt, 80 * hg + 64, 128 * r, bars + 8 * B_QF);
      }
    } else if (w == 1) {
      unsigned epoch = 0;
      if (lane == 0) {
        epoch = atomicAdd(g_cnt + C_LAUNCH, 1u) / NCTA;
        asm volatile("st.shared.u32 [%0], %1;" ::"r"(sb + OFF_EPOCH), "r"(epoch) : "memory");
        mbar_arrive(bars + 8 * B_EPOCH);
        mbar_wait(bars + 8 * B_KVD, 0);
        mbar_expect_tx(bars + 8 * B_HB, 5 * 4096);
#pragma unroll 1
        for (int c = 0; c < 5; c++) {
          if (c == 3) mbar_wait(bars + 8 * B_S3, 0);
          bulk_load(sb + off_ch(c) + U_BYTES, p.ssm_k + (5 * b + c) * SEQ, 4096, bars + 8 * B_HB);
        }
#pragma unroll
        for (int c = 0; c < 4; c++) mbar_expect_tx(bars + 8 * (B_U + c), c < 3 ? U_BYTES : 2 * U_BYTES);
        const uint4* usrc = g_U + 5 * b * U_PITCH;
        mbar_wait(bars + 8 * B_USIG, 0);
        flag_wait(g_cnt + C_PREP + 32 * (b & 15), (epoch + 1) * NCTA);
        TS(23);
#pragma unroll
        for (int c = 0; c < 5; c++) {
          if (c == 3 && U_TRIM) mbar_wait(bars + 8 * (B_U + 2), 0);
          bulk_load(sb + off_ch(c), usrc + c * U_PITCH, U_BYTES, bars + 8 * (B_U + (c < 3 ? c : 3)));
          TSIF(c == 0 || c == 4, 116 + (c >> 2));
        }
      }
      epoch = __shfl_sync(0xffffffffu, epoch, 0);
      if (lane < 8) {
        const int src = (b & ~7) | step_src(hg, lane);
        mbar_wait(bars + 8 * OP_TRIG, 0);
        TS(20);
        bool seen = false;
#pragma unroll 1
        for (int spins = 0; spins < SPIN_LIMIT; spins++) {
          const bool now = !seen && (int)(flag_read(g_cnt + C_O + 32 * src) - (epoch + 1)) >= 0;
          if (now && lane >= 1 && lane < 4) bulk_load(sb + off_o(lane), g_O + src * 1280, O_BYTES, bars + 8 * (B_FULL2 + lane));
          seen = seen || now;
          if (__all_sync(0xff, seen)) break;
        }
        TS(21);
        if (lane == 5) bulk_load(sb + OFF_GATE, g_gate + 128 * r, 512, bars + 8 * (B_FULL2 + 5));
#pragma unroll 1
        for (int j = 4; j < 8; j++) {
          if (lane == j) {
            mbar_wait(bars + 8 * (j < 6 ? B_C34 : B_EMPTY2 + j - 6), 0);
            if (RF_GATE && j == 6) mbar_wait(bars + 8 * B_YSIG, 0);
            bulk_load(sb + off_o(j), g_O + src * 1280, O_BYTES, bars + 8 * (B_FULL2 + j));
          }
          __syncwarp(0xff);
        }
        TS(22);
      }
    } else if (w == 2) {
      mbar_wait(bars + 8 * B_PREP, 0);
      flag_signal(g_cnt + C_PREP, 16, lane);
      TS(25);
      if (lane == 0) mbar_arrive(bars + 8 * B_USIG);
      mbar_wait(bars + 8 * B_GATE, 0);
      if (G_TMA) {
        if (lane == 0) {
          asm volatile("cp.async.bulk.global.shared::cta.bulk_group [%0], [%1], 64;\ncp.async.bulk.commit_group;\n"
                       "cp.async.bulk.wait_group.read 0;" ::"l"(g_gate + 16 * b), "r"(sb + OFF_GATE + 64 * hg) : "memory");
          bulk_load(sb + OFF_GATE + 64 * hg, g_gate + 16 * b, 64, bars + 8 * B_ORB);
        }
      } else if (((NOMB & 1) || O_RB) && lane == 0) {
        asm volatile("fence.release.gpu;" ::: "memory");
      }
      mbar_wait(bars + 8 * B_ATTN, 0);
      if (lane == 0) {
        if (O_DEFER) mbar_wait(bars + 8 * (B_U + 3), 0);
        asm volatile("cp.async.bulk.global.shared::cta.bulk_group [%0], [%1], 20480;\ncp.async.bulk.commit_group;"
                     ::"l"(g_O + b * 1280), "r"(sb + OFF_OA) : "memory");
        if (O_RB == 2) {
          asm volatile("cp.async.bulk.wait_group.read 0;" ::: "memory");
          mbar_expect_tx(bars + 8 * B_ORB, O_BYTES + 64 * G_TMA);
          bulk_load(sb + OFF_OA, g_O + b * 1280, O_BYTES, bars + 8 * B_ORB);
          mbar_wait(bars + 8 * B_ORB, 0);
          flag_bump(g_cnt + C_O + 32 * b);
        } else if (O_RB) asm volatile("cp.async.bulk.wait_group.read 0;" ::: "memory");
        else asm volatile("cp.async.bulk.wait_group 0;\nfence.proxy.async.global;" ::: "memory");
      }
      TS(74);
      if (O_RB == 2) {
      } else if (O_RB) {
        __syncwarp();
        unsigned v[5];
#pragma unroll
        for (int c = 0; c < 5; c++) v[c] = flag_read(reinterpret_cast<const unsigned*>(g_O + b * 1280 + 256 * c + 8 * lane + 7));
        const unsigned dep = __reduce_or_sync(0xffffffffu, (v[0] ^ v[1] ^ v[2] ^ v[3] ^ v[4]) & p.zero);
        if (lane == 0) flag_bump(g_cnt + C_O + 32 * b + dep);
      } else if (!(NOMB & 1)) flag_signal(g_cnt + C_O + 32 * b, 1, lane);
      else if (lane == 0) flag_bump(g_cnt + C_O + 32 * b);
      TS(26);
      if (lane == 0) mbar_arrive(bars + 8 * B_OSIG);

    } else {
      if (lane == 0) {
        uint4* dst = g_WO + (hg * 8 + (r >> 1)) * 800 + (r & 1) * 80;
        if (WPF) {
          mbar_wait(bars + 8 * WPF, 0);
          if (WPF_LIN)
            asm volatile("cp.async.bulk.prefetch.L2.global [%0], 6400;" ::"l"(p.wo + b * 3200) : "memory");
          else
            asm volatile("cp.async.bulk.prefetch.tensor.3d.L2.global [%0, {%1, %2, %3}];" ::"l"(&m.wo), "r"(0), "r"(40 * r), "r"(5 * hg) : "memory");
        }
        mbar_wait(bars + 8 * B_P1, 0);
        mbar_wait(bars + 8 * WB_TRIG, 0);
        mbar_expect_tx(bars + 8 * B_WST, WO_BYTES / 2);
        tma_3d(sb + OFF_WS, &m.wo, 0, 40 * r, 5 * hg, bars + 8 * B_WST);
        mbar_wait(bars + 8 * B_WST, 0);
        mbar_wait(bars + 8 * WO_TRIG, 0);
#pragma unroll 1
        for (int n = 0; n < 5; n++)
          asm volatile("cp.async.bulk.global.shared::cta.bulk_group [%0], [%1], 1280;" ::"l"(dst + 160 * n), "r"(sb + OFF_WS + 1280 * n) : "memory");
        if (W_RB) {
          asm volatile("cp.async.bulk.commit_group;\ncp.async.bulk.wait_group.read 0;" ::: "memory");
          mbar_expect_tx(bars + 8 * B_WST, WO_BYTES / 2);
#pragma unroll 1
          for (int n = 0; n < 5; n++) bulk_load(sb + OFF_WS + 1280 * n, dst + 160 * n, 1280, bars + 8 * B_WST);
          mbar_wait(bars + 8 * B_WST, 1);
        } else {
          asm volatile("cp.async.bulk.commit_group;\ncp.async.bulk.wait_group 0;\nfence.proxy.async.global;" ::: "memory");
          if (!(NOMB & 4)) asm volatile("fence.release.gpu;" ::: "memory");
        }
        flag_bump(g_cnt + C_W + 32 * hg);
        mbar_arrive(bars + 8 * B_WOP);
        TS(71);
        mbar_expect_tx(bars + 8 * B_C34, 3 * U_BYTES);
        mbar_expect_tx(bars + 8 * B_YRB, 2 * U_BYTES);
#pragma unroll 1
        for (int c = 0; c < 5; c++) {
          mbar_wait(bars + 8 * (B_YST + c), 0);
          asm volatile("cp.async.bulk.global.shared::cta.bulk_group [%0], [%1], 4096;\ncp.async.bulk.commit_group;\n"
                       "cp.async.bulk.wait_group.read 0;" ::"l"(g_Y + (5 * b + c) * Y_PITCH), "r"(sb + off_ch(c)) : "memory");
          bulk_load(sb + off_ch(c), g_Y + (5 * b + c) * Y_PITCH, U_BYTES, bars + 8 * (c < 3 ? B_C34 : B_YRB));
        }
        TS(75);
        mbar_wait(bars + 8 * B_C34, 0);
        mbar_wait(bars + 8 * B_YRB, 0);
        flag_bump(g_cnt + C_Y + 32 * (b >> 4));
        TS(27);
        mbar_arrive(bars + 8 * B_YSIG);
        mbar_expect_tx(bars + 8 * B_YFULL, 20480);
        flag_wait(g_cnt + C_Y + 32 * hg, (lds32(sb + OFF_EPOCH) + 1) * 16);
        TS(24);
        tma_2d(sb + OFF_YT, &m.y, 128 * r, 80 * hg, bars + 8 * B_YFULL);
        tma_2d(sb + OFF_YT + 10240, &m.y, 128 * r + 64, 80 * hg, bars + 8 * B_YFULL);
      }
    }
  } else {
    asm volatile("setmaxnreg.inc.sync.aligned.u32 152;");
    if (wg < 2) {
      float acc[120];
#pragma unroll
      for (int i = 0; i < 120; i++) acc[i] = 0.f;
      const uint32_t da = desc_lo(sb + wg * 8192, 16), db = desc_lo(sb + ST_W, 8192), dc = desc_lo(sb + ST_WT, 2048);
      if (PW1) pin<120>(acc);
      if (PW1 == 2) mbar_wait(bars + 8 * B_FULL1, 0);
#pragma unroll 1
      for (int kb = 0; kb < 10; kb++) {
        mbar_wait(bars + 8 * (B_FULL1 + (kb & 3)), (kb >> 2) & 1);
        const uint32_t so = (kb & 3) * (STAGE_BYTES >> 4);
        wg_fence();
#pragma unroll
        for (int k = 0; k < 4; k++) {
          WgSST<192>::mma<HI_SW128, HI_SW128>(acc, da + so + 2 * k, db + so + 128 * k, 1);
          WgSST<48>::mma<HI_SW128, HI_SW32>(acc + 96, da + so + 2 * k, dc + so + 32 * k, 1);
        }
        wg_commit();
        wg_wait<1>();
        if (kb > 0 && lane == 0) mbar_arrive(bars + 8 * (kb == 4 ? B_E3 : B_EMPTY1 + ((kb - 1) & 3)));
      }
      mbar_wait(bars + 8 * B_EPOCH, 0);
      const uint32_t tag = lds32(sb + OFF_EPOCH) + 1;
      mbar_wait(bars + 8 * B_S3, 0);
      wg_wait<0>();
      pin<120>(acc);
      if (lane == 0) mbar_arrive(bars + 8 * B_P1);
      TSM(w == 0, 3 + wg);
      attention(acc, sb, b, wg, w, lane, tag, p.zero);
    } else {
      const int tw = tid & 127, chl = 64 * (b & 1) + 8 * w + (lane >> 2);
      uint4* up = g_U + chl * U_PITCH + ((4 * (b >> 1) + (lane & 3)) ^ ((b >> 2) & 1));
      uint2 sw[10];
      uint32_t dv = 0;
      if (lane < 5) dv = __ldg(reinterpret_cast<const unsigned short*>(p.ssm_D) + 5 * b + lane);
#pragma unroll
      for (int i = 0; i < 10; i++) sw[i] = ldg64(reinterpret_cast<const uint2*>(p.shift_k) + chl + 128 * (i >> 1) + 32 * (i & 1));
      uint32_t tab[12];
      uint32_t tt[2];
      fft_tables(tab, tw);
      fft_twiddles(tt, tw);
      uint4 res[10];
#pragma unroll
      for (int i = 0; i < 10; i++) res[i] = make_uint4(0, 0, 0, 0);
#pragma unroll 1
      for (int slab = 0; slab < 5; slab++) {
#pragma unroll
        for (int i = 0; i < 8; i++) res[i] = res[i + 2];
        prep_slab(res + 8, sw, sb, slab, w, lane);
        TSIF(w == 0, 99 + 4 * slab);
#pragma unroll
        for (int i = 0; i < 8; i++) sw[i] = sw[i + 2];
      }
      TSIF(w == 0, 28);
      __syncwarp();
      if (lane == 0) mbar_arrive(bars + 8 * B_KVD + ((res[8].x ^ res[9].x) & p.zero));
      mbar_wait(bars + 8 * B_KVD, 0);
      fft_tables_store(tab, sb, tw);
      mbar_wait(bars + 8 * B_LAST, 0);
#pragma unroll
      for (int i = 0; i < 10; i++) up[(128 * (i >> 1) + 32 * (i & 1)) * U_PITCH] = res[i];
      __syncwarp();
      if (lane == 0) mbar_arrive(bars + 8 * B_PREP);
      TSIF(w == 0 && !U_TMA, 5);
      mbar_wait(bars + 8 * (G_AFTER ? B_USIG : B_LAST), 0);
      prep_gate(p, sb, b, w, lane);
      __syncwarp();
      if (lane == 0) mbar_arrive(bars + 8 * B_GATE);
      TSIF(w == 0, 72);
      mbar_wait(bars + 8 * B_HB, 0);
      TSIF(w == 0, 2);
      const uint32_t ha = sb + U_BYTES + ((tw >> 3) * 16 + 8 + (tw & 7)) * 16;
      uint4 hv[5];
#pragma unroll
      for (int c = 0; c < 5; c++) hv[c] = lds128(ha + off_ch(c));
      __syncwarp();
#pragma unroll
      for (int c = 0; c < 5; c++) sts128((ha ^ 16) + off_ch(c), hv[c].x, hv[c].y, hv[c].z, hv[c].w);
      asm volatile("st.shared.v2.u32 [%0], {%1, %2};" ::"r"(sb + OFF_TT + 8 * tw), "r"(tt[0]), "r"(tt[1]) : "memory");
      if (tw < 5) asm volatile("st.shared.f32 [%0], %1;" ::"r"(sb + OFF_D + 4 * tw), "f"(bf_lo(dv) * 0.125f) : "memory");
      fence_async_smem();
      __syncwarp();
      if (lane == 0) mbar_arrive(bars + 8 * B_HA);
      TSIF(w == 0, 6);
    }

    FftConst fc;
    TSM(w == 0 && wg == 0, 104);
    mbar_wait(bars + 8 * B_HA, 0);
    fft_matrices(fc, sb, w, lane);
    TSM(w == 0 && wg == 0, 105);
    TSM(w == 0 && wg == 2, 124);
#pragma unroll 1
    for (uint32_t tasks = wg == 0 ? TASK0 : wg == 1 ? TASK1 : TASK2; tasks; tasks >>= 4) {
      const int c = (tasks & 7) - 1;
      conv_channel(fc, sb, c, wg, w, lane);
      if (lane == 0) mbar_arrive(bars + 8 * (B_YST + c));
      TSM(w == 0, 10 + c);
    }

    if (wg < 2) {
      const int g = lane >> 2;
      float acc[40];
#pragma unroll
      for (int i = 0; i < 40; i++) acc[i] = 0.f;
      const uint32_t da = desc_lo(sb + wg * 1024, 2048), db = desc_lo(sb, 2560);
      if (!WO_FAST) mbar_wait(bars + 8 * (O_RB == 2 ? B_ORB : B_ATTN), 0);
      mbar_wait(bars + 8 * (B_YST + 3), 0);
      mbar_wait(bars + 8 * (B_YST + 4), 0);
      if (PW2 && !WO_FAST) mbar_wait(bars + 8 * B_FULL2, 0);
      TSM(w == 0, 15 + wg);
#pragma unroll 1
      for (int j = 0; j < 8; j++) {
        mbar_wait(bars + 8 * (B_FULL2 + j), 0);
        const uint32_t oa = da + (off_o(j) >> 4), ob = db + (off_w(j) >> 4);
        wg_fence();
#pragma unroll
        for (int k = 0; k < 5; k++) WgSST<80>::mma<HI_NONE, HI_SW32>(acc, oa + 256 * k, ob + 32 * k, 1);
        wg_commit();
        wg_wait<1>();
        if (j >= 1 && j <= Q_SLOT + 1 && lane == 0) mbar_arrive(bars + 8 * (B_EMPTY2 + j - 1));
      }
      TSIF(w == 0 && wg == 0, 113);
      const int tr = 64 * wg + 16 * w + (lane & 15);
      const uint32_t fm = sb + OFF_QS + tr * 128, fx = (lane >> 4) ^ (tr & 7), fq = sb + OFF_QS + tr * 160 + (lane >> 4) * 16;
      const uint32_t ft = sb + OFF_QT + tr * 32 + (((lane >> 4) ^ (tr >> 2)) & 1) * 16;
      const float g0 = __uint_as_float(lds32(sb + OFF_GATE + (64 * wg + 16 * w + g) * 4));
      const float g1 = __uint_as_float(lds32(sb + OFF_GATE + (64 * wg + 16 * w + 8 + g) * 4));
      const uint32_t ga = pack2(g0, g0), gb = pack2(g1, g1);
      const uint32_t na = pack2(1.f - g0, 1.f - g0), nb = pack2(1.f - g1, 1.f - g1);

      uint32_t qf[20];
      mbar_wait(bars + 8 * B_QF, 0);
#pragma unroll
      for (int j = 0; j < 5; j++) ldsm4(qf + 4 * j, QBOX ? fq + 32 * j : j < 4 ? fm + ((fx ^ (2 * j)) << 4) : ft);
      if (FUSE_MIX) {
#pragma unroll
        for (int i = 0; i < 20; i++) {
          qf[i] = bmul((i & 1) ? gb : ga, qf[i]);
          asm volatile("" : "+r"(qf[i]));
        }
      }
      wg_wait<0>();
      pin<40>(acc);
      TSM(w == 0, 17 + wg);
      uint32_t pb[20];
#pragma unroll
      for (int j = 0; j < 10; j++) {
        pb[2 * j] = bmul(na, pack2(acc[4 * j], acc[4 * j + 1]));
        pb[2 * j + 1] = bmul(nb, pack2(acc[4 * j + 2], acc[4 * j + 3]));
        asm volatile("" : "+r"(pb[2 * j]), "+r"(pb[2 * j + 1]));
      }
      const uint32_t ya = sb + OFF_YT + wg * 10240 + ((lane >> 4) * 8 + (lane & 7)) * 128 +
                          (((2 * w + (((lane >> 3) & 1) ^ wg)) ^ (lane & 7)) << 4);
      mbar_wait(bars + 8 * B_YFULL, 0);
      TSM(w == 0 && wg == 0, 19);
#pragma unroll
      for (int j = 0; j < 5; j++) {
        uint32_t y[4];
        ldsm4t(y, ya + 2048 * j);
#pragma unroll
        for (int i = 0; i < 4; i++)
          qf[4 * j + i] = FUSE_MIX ? bfma(qf[4 * j + i], y[i], pb[4 * j + i]) : badd(bmul((i & 1) ? gb : ga, bmul(qf[4 * j + i], y[i])), pb[4 * j + i]);
      }
#pragma unroll
      for (int j = 0; j < 5; j++) stsm4(QBOX ? fq + 32 * j : j < 4 ? fm + ((fx ^ (2 * j)) << 4) : ft, qf + 4 * j);
      fence_async_smem();
      __syncwarp();
      if (lane == 0) {
        const int row = 64 * wg + 16 * w;
        asm volatile("cp.async.bulk.tensor.2d.global.shared::cta.bulk_group [%0, {%2, %3}], [%1];"
                     ::"l"(&m.om), "r"(sb + OFF_QS + row * (QBOX ? 160 : 128)), "r"(80 * hg), "r"(128 * r + row) : "memory");
        if (!QBOX) asm volatile("cp.async.bulk.tensor.2d.global.shared::cta.bulk_group [%0, {%2, %3}], [%1];"
                     ::"l"(&m.ot), "r"(sb + OFF_QT + row * 32), "r"(80 * hg + 64), "r"(128 * r + row) : "memory");
        asm volatile("cp.async.bulk.commit_group;\ncp.async.bulk.wait_group.read 0;" ::: "memory");
      }
      TSM(true, 40 + 4 * wg + w);
      if (ENDBAR) asm volatile("bar.sync 15, 256;" ::: "memory");
    }
  }
}

typedef CUresult (*EncodeFn)(CUtensorMap*, CUtensorMapDataType, cuuint32_t, void*, const cuuint64_t*, const cuuint64_t*,
                             const cuuint32_t*, const cuuint32_t*, CUtensorMapInterleave, CUtensorMapSwizzle,
                             CUtensorMapL2promotion, CUtensorMapFloatOOBfill);

void encode(EncodeFn fn, CUtensorMap* tm, const void* base, int rank, const cuuint64_t* dims, const cuuint64_t* strides,
            const cuuint32_t* box, CUtensorMapSwizzle swz) {
  const cuuint32_t ones[3] = {1, 1, 1};
  fn(tm, CU_TENSOR_MAP_DATA_TYPE_BFLOAT16, rank, const_cast<void*>(base), dims, strides, box, ones,
     CU_TENSOR_MAP_INTERLEAVE_NONE, swz, CU_TENSOR_MAP_L2_PROMOTION_L2_128B, CU_TENSOR_MAP_FLOAT_OOB_FILL_NONE);
}

}

extern "C" void kernel_launch(void* const* d_in, const int* in_sizes, int n_in, void* d_out, int out_size) {
  (void)in_sizes; (void)n_in; (void)out_size;
  Params p;
  p.q = (const __nv_bfloat16*)d_in[0];
  p.k = (const __nv_bfloat16*)d_in[1];
  p.v = (const __nv_bfloat16*)d_in[2];
  p.shift_k = (const __nv_bfloat16*)d_in[3];
  p.ssm_k = (const __nv_bfloat16*)d_in[4];
  p.ssm_D = (const __nv_bfloat16*)d_in[5];
  p.wqkv = (const __nv_bfloat16*)d_in[7];
  p.wo = (const __nv_bfloat16*)d_in[8];
  p.gate_w = (const __nv_bfloat16*)d_in[9];
  p.out = (__nv_bfloat16*)d_out;
  p.zero = 0;

  static EncodeFn fn = nullptr;
  static void *yaddr = nullptr, *uaddr = nullptr;
  if (!fn) {
    cudaDriverEntryPointQueryResult qr;
    void* f = nullptr;
    cudaGetDriverEntryPoint("cuTensorMapEncodeTiled", &f, cudaEnableDefault, &qr);
    fn = (EncodeFn)f;
    cudaGetSymbolAddress(&yaddr, g_Y);
    cudaGetSymbolAddress(&uaddr, g_U);
    cudaFuncSetAttribute(fused_kernel, cudaFuncAttributeMaxDynamicSharedMemorySize, SMEM_BYTES);
  }
  Maps m;
  {
    const cuuint64_t dims[3] = {640, 1024, 2}, st[2] = {2560, 1280};
    const cuuint32_t box[3] = {64, 64, 2};
    encode(fn, &m.x, p.q, 3, dims, st, box, CU_TENSOR_MAP_SWIZZLE_128B);
  }
  {
    const cuuint64_t dims[3] = {640, 640, 3}, st[2] = {3840, 1280};
    const cuuint32_t box[3] = {64, 64, 3}, boxt[3] = {16, 64, 3};
    encode(fn, &m.wm, p.wqkv, 3, dims, st, box, CU_TENSOR_MAP_SWIZZLE_128B);
    encode(fn, &m.wt, p.wqkv, 3, dims, st, boxt, CU_TENSOR_MAP_SWIZZLE_32B);
  }
  {
    const cuuint64_t dims[3] = {64, 2048, 10}, st[2] = {1280, 128};
    const cuuint32_t boxk[3] = {64, 35, 1}, boxv[3] = {64, 32, 1};
    encode(fn, &m.k, p.k, 3, dims, st, boxk, CU_TENSOR_MAP_SWIZZLE_128B);
    encode(fn, &m.v, p.v, 3, dims, st, boxv, CU_TENSOR_MAP_SWIZZLE_128B);
  }
  {
    const cuuint64_t dims[3] = {16, 640, 40}, st[2] = {1280, 32};
    const cuuint32_t box[3] = {16, 40, 5};
    encode(fn, &m.wo, p.wo, 3, dims, st, box, CU_TENSOR_MAP_SWIZZLE_32B);
  }
  {
    const cuuint64_t dims[2] = {2048, 640}, st[1] = {Y_PITCH * 16};
    const cuuint32_t box[2] = {64, 80};
    encode(fn, &m.y, yaddr, 2, dims, st, box, CU_TENSOR_MAP_SWIZZLE_128B);
    const cuuint64_t stu[1] = {U_PITCH * 16};
    const cuuint32_t boxu[2] = {32, 64};
    encode(fn, &m.u, uaddr, 2, dims, stu, boxu, CU_TENSOR_MAP_SWIZZLE_NONE);
  }
  {
    const cuuint64_t dims[2] = {640, 2048}, st[1] = {1280};
    const cuuint32_t bqm[2] = {QBOX ? 80 : 64, 128}, bqt[2] = {16, 128}, bom[2] = {QBOX ? 80 : 64, 16}, bot[2] = {16, 16};
    encode(fn, &m.qm, p.q, 2, dims, st, bqm, QBOX ? CU_TENSOR_MAP_SWIZZLE_NONE : CU_TENSOR_MAP_SWIZZLE_128B);
    encode(fn, &m.qt, p.q, 2, dims, st, bqt, CU_TENSOR_MAP_SWIZZLE_32B);
    encode(fn, &m.om, p.out, 2, dims, st, bom, QBOX ? CU_TENSOR_MAP_SWIZZLE_NONE : CU_TENSOR_MAP_SWIZZLE_128B);
    encode(fn, &m.ot, p.out, 2, dims, st, bot, CU_TENSOR_MAP_SWIZZLE_32B);
  }
  fused_kernel<<<NCTA, NTHR, SMEM_BYTES>>>(m, p);
}
```

```cpp
#include <cuda.h>
#include <cuda_bf16.h>
#include <cuda_runtime.h>
#include <stdint.h>

namespace {

constexpr int SEQ = 2048, DIM = 640, NCTA = 128, NTHR = 512;

#define TRIG_KB 9
#define KV_KB 2
#define DEV_EXIT 0
#define ATT_GATE 0
#define G_AFTER 0
#define FENCE_LO 0
#define FENCE_HI 0
#define PW1 2
#define PW2 1
#define ENDBAR 0
#define PAD_KB 0
#define Y_ALIAS 1
#define NOMB 0
#define SRC_ROT 0
#define WAIT_NS 0
#define WB_TRIG B_USIG
#define G_POS 0
#define TAILF 1
#define T_ISSUE 384
#define T_PF 416
#define T_INIT 448
#define ATT_MERGE 0
#define BMAP 1
#define PRE2 1
#define KV_MIX 0
#define O_DEFER 0
#define TASK0 0x52
#define TASK1 0x3
#define TASK2 0x41
#define HALO_FIRST 1
#define PREV_EARLY 0
#define Y_RB 2
#define O_RB 2
#define O_EAGER 1
#define OP_TRIG B_ATTN
#define FUSE_MIX 1
#define Q_EARLY 1
#define WO_FAST 0
#define U_TRIM 1
#define Q_SLOT 3
#define G_TMA 1
#define W_RB 1
#define WPF B_S3
#define WPF_LIN 1
#define QBOX 0
#define ACQ 0
#define U_TMA 0
#define U_GATE 0
#define RF_GATE 0
#define WO_TRIG B_WST
#define WL_TRIG B_WOP
#define WO_GATE 1

constexpr uint32_t STAGE_BYTES = 47104, ST_W = 16384, ST_WT = 40960;
constexpr uint32_t O_BYTES = 20480, WO_BYTES = 12800;
constexpr uint32_t OFF_OA = 0;
constexpr uint32_t OFF_QS = Q_SLOT * O_BYTES, OFF_QT = OFF_QS + 16384;
constexpr uint32_t OFF_WC = 81920;
constexpr uint32_t OFF_WA = 94720;
constexpr uint32_t OFF_GATE = 145920;
constexpr uint32_t OFF_TT = 146432;
constexpr uint32_t OFF_KVX = 148480;
constexpr uint32_t OFF_CH3 = 163840;
constexpr uint32_t CH_BYTES = 12288, U_BYTES = 4096;
constexpr uint32_t OFF_FT = 225280, OFF_GT = 229376;
constexpr uint32_t OFF_CH0 = 188416;
constexpr uint32_t OFF_KVS = OFF_CH0, KVS_V = 4480, KVS_BYTES = 8576;
constexpr uint32_t OFF_WS = OFF_WA;
__device__ __forceinline__ uint32_t off_us(int s) { return OFF_CH0 + 4096 * ((0x65320 >> (4 * s)) & 7); }
constexpr uint32_t OFF_YT = 163840;
constexpr uint32_t OFF_BAR = 231936;
constexpr uint32_t SMEM_BYTES = OFF_BAR + 512;

enum : uint32_t {
  B_FULL1 = 0, B_EMPTY1 = 4, B_S3 = 7, B_FULL2 = 52, B_EMPTY2 = 13, B_U = 8, B_GATE = 12, B_HA = 19, B_HB = 20,
  B_ATTN = 21, B_C34 = 22, B_YRB = 23, B_YFULL = 24, B_EPOCH = 25, B_PREP = 26, B_P1 = 27, B_LAST = 28,
  B_E3 = 29, B_OSIG = 30, B_WOP = 31, B_USIG = 32, B_WST = 33, B_KV = 34, B_KVD = 39, B_QF = 17, B_ATT2 = 18, B_YST = 40,
  B_ORB = 45, B_US = 45, B_YSIG = 50
};
constexpr uint32_t OFF_EPOCH = OFF_BAR + 8 * 51, OFF_D = OFF_BAR + 8 * 60;
__device__ __forceinline__ uint32_t off_o(int j) { return j < 4 ? OFF_OA + j * O_BYTES : j < 6 ? OFF_CH0 + (j - 4) * O_BYTES : OFF_OA + (j - 6) * O_BYTES; }
__device__ __forceinline__ uint32_t off_w(int j) { return j < 4 ? OFF_WA + j * WO_BYTES : j == 4 ? OFF_KVX : j == 5 ? OFF_WC : OFF_WA + (j - 6) * WO_BYTES; }
__device__ __forceinline__ int step_src(int hg, int j) {
  if (SRC_ROT == 2) {
    const int pos = (0x37621540 >> (4 * hg)) & 7;
    return j == 0 ? hg : (0x65217430 >> (4 * (j <= pos ? j - 1 : j))) & 7;
  }
  return SRC_ROT ? (hg + j) & 7 : j == 0 ? hg : j <= hg ? j - 1 : j;
}
__device__ __forceinline__ bool tail_first(int hg) { return TAILF && (hg & 3) == 3; }
__device__ __forceinline__ uint32_t off_ch(int c) { return (c < 3 ? OFF_CH0 : OFF_CH3 - 3 * CH_BYTES) + c * CH_BYTES; }

#define U_PITCH 264
__device__ __align__(1024) uint4 g_U[DIM * U_PITCH];
__device__ uint4 g_O[NCTA * 1280];
#define g_Y g_U
constexpr int Y_PITCH = U_PITCH;
__device__ uint4 g_WO[64 * 800];
__device__ uint4 g_halo[NCTA * 2 * 7 * 32];
__device__ __align__(128) float g_gate[SEQ + PAD_KB * 256];
__device__ unsigned g_cnt[32 * (1 + 2 * 16 + 8 + NCTA)];
constexpr int C_LAUNCH = 0, C_PREP = 32, C_Y = 32 * 17, C_W = 32 * 33, C_O = 32 * 41;

#define TSM(cond, slot) do { } while (0)
#define TSIF(cond, slot) do { if (__LINE__ >= FENCE_LO && __LINE__ < FENCE_HI) sched_fence(); } while (0)
__device__ __forceinline__ void sched_fence() {
  asm volatile("{\n.reg .pred p;\n.reg .u32 c;\nmov.u32 c, %%clock;\nsetp.eq.u32 p, c, 0;\n@p st.shared.u32 [%0], c;\n}"
               ::"r"(1024 + OFF_EPOCH + 4) : "memory");
}
#define TS(slot) TSIF(true, slot)

struct Params {
  const __nv_bfloat16 *q, *k, *v, *shift_k, *ssm_k, *ssm_D, *wqkv, *wo, *gate_w;
  __nv_bfloat16* out;
  uint32_t zero;
};

#define POLL_NS 0
constexpr int SPIN_LIMIT = 1 << 17;

__device__ __forceinline__ void mbar_init(uint32_t bar, uint32_t count) {
  asm volatile("mbarrier.init.shared::cta.b64 [%0], %1;" ::"r"(bar), "r"(count) : "memory");
}
__device__ __forceinline__ void mbar_expect_tx(uint32_t bar, uint32_t bytes) {
  asm volatile("mbarrier.arrive.expect_tx.shared::cta.b64 _, [%0], %1;" ::"r"(bar), "r"(bytes) : "memory");
}
__device__ __forceinline__ void mbar_arrive(uint32_t bar) {
  asm volatile("mbarrier.arrive.shared::cta.b64 _, [%0];" ::"r"(bar) : "memory");
}
__device__ __forceinline__ void mbar_wait(uint32_t bar, uint32_t parity) {
  uint32_t ok;
  int spins = 0;
  do {
    if (WAIT_NS)
      asm volatile("{\n.reg .pred p;\nmbarrier.try_wait.parity.shared::cta.b64 p, [%1], %2, %3;\nselp.b32 %0, 1, 0, p;\n}"
                   : "=r"(ok) : "r"(bar), "r"(parity), "r"(WAIT_NS) : "memory");
    else
      asm volatile("{\n.reg .pred p;\nmbarrier.try_wait.parity.shared::cta.b64 p, [%1], %2;\nselp.b32 %0, 1, 0, p;\n}"
                   : "=r"(ok) : "r"(bar), "r"(parity) : "memory");
    if (++spins > SPIN_LIMIT) break;
  } while (!ok);
}
__device__ __forceinline__ unsigned flag_read(const unsigned* p) {
  unsigned v;
  asm volatile("ld.relaxed.gpu.global.u32 %0, [%1];" : "=r"(v) : "l"(p) : "memory");
  return v;
}
__device__ __forceinline__ void flag_poll(const unsigned* p, unsigned target) {
  unsigned v;
  int spins = 0;
  do {
    if (POLL_NS && spins) __nanosleep(POLL_NS);
    asm volatile("ld.relaxed.gpu.global.u32 %0, [%1];" : "=r"(v) : "l"(p) : "memory");
    if (++spins > SPIN_LIMIT) break;
  } while ((int)(v - target) < 0);
}
__device__ __forceinline__ void flag_wait(const unsigned* p, unsigned target) {
  flag_poll(p, target);
  if (ACQ) asm volatile("fence.acquire.gpu;\nfence.proxy.async.global;" ::: "memory");
}
__device__ __forceinline__ void flag_signal(unsigned* p, int n, int lane) {
  if (lane == 0) asm volatile("fence.release.gpu;" ::: "memory");
  __syncwarp();
  if (lane < n) asm volatile("red.relaxed.gpu.global.add.u32 [%0], 1;" ::"l"(p + 32 * lane) : "memory");
}
__device__ __forceinline__ void flag_bump(unsigned* p) {
  asm volatile("red.relaxed.gpu.global.add.u32 [%0], 1;" ::"l"(p) : "memory");
}
__device__ __forceinline__ void fence_async_smem() { asm volatile("fence.proxy.async.shared::cta;" ::: "memory"); }
__device__ __forceinline__ void wg_sync(int id) { asm volatile("bar.sync %0, 128;" ::"r"(id) : "memory"); }

__device__ __forceinline__ void tma_2d(uint32_t dst, const CUtensorMap* tm, int c0, int c1, uint32_t bar) {
  asm volatile("cp.async.bulk.tensor.2d.shared::cluster.global.mbarrier::complete_tx::bytes [%0], [%1, {%3, %4}], [%2];"
               ::"r"(dst), "l"(tm), "r"(bar), "r"(c0), "r"(c1) : "memory");
}
__device__ __forceinline__ void tma_3d(uint32_t dst, const CUtensorMap* tm, int c0, int c1, int c2, uint32_t bar) {
  asm volatile("cp.async.bulk.tensor.3d.shared::cluster.global.mbarrier::complete_tx::bytes [%0], [%1, {%3, %4, %5}], [%2];"
               ::"r"(dst), "l"(tm), "r"(bar), "r"(c0), "r"(c1), "r"(c2) : "memory");
}
__device__ __forceinline__ void bulk_load(uint32_t dst, const void* src, uint32_t bytes, uint32_t bar) {
  asm volatile("cp.async.bulk.shared::cluster.global.mbarrier::complete_tx::bytes [%0], [%1], %2, [%3];"
               ::"r"(dst), "l"(src), "r"(bytes), "r"(bar) : "memory");
}
__device__ __forceinline__ void tm_prefetch(const CUtensorMap* tm) {
  asm volatile("prefetch.tensormap [%0];" ::"l"(tm) : "memory");
}

__device__ __forceinline__ void wg_fence() { asm volatile("wgmma.fence.sync.aligned;" ::: "memory"); }
__device__ __forceinline__ void wg_commit() { asm volatile("wgmma.commit_group.sync.aligned;" ::: "memory"); }
template <int N> __device__ __forceinline__ void wg_wait() { asm volatile("wgmma.wait_group.sync.aligned %0;" ::"n"(N) : "memory"); }
__device__ __forceinline__ uint32_t desc_lo(uint32_t addr, uint32_t lbo) { return ((addr & 0x3FFFF) >> 4) | ((lbo >> 4) << 16); }
constexpr uint32_t desc_hi(uint32_t sbo, uint32_t swz) { return (sbo >> 4) | (swz << 30); }
constexpr uint32_t HI_SW128 = desc_hi(1024, 1), HI_SW64 = desc_hi(512, 2), HI_SW32 = desc_hi(256, 3), HI_NONE = desc_hi(128, 0);
template <int N> __device__ __forceinline__ void pin(float* d) {
#pragma unroll
  for (int i = 0; i < N; i++) asm volatile("" : "+f"(d[i])::"memory");
}

__device__ __forceinline__ uint32_t lds32(uint32_t a) {
  uint32_t v;
  asm volatile("ld.volatile.shared.u32 %0, [%1];" : "=r"(v) : "r"(a) : "memory");
  return v;
}
__device__ __forceinline__ uint4 ldg128(const void* a) {
  uint4 v;
  asm volatile("ld.global.nc.v4.u32 {%0, %1, %2, %3}, [%4];" : "=r"(v.x), "=r"(v.y), "=r"(v.z), "=r"(v.w) : "l"(a) : "memory");
  return v;
}
__device__ __forceinline__ uint2 ldg64(const void* a) {
  uint2 v;
  asm volatile("ld.global.nc.v2.u32 {%0, %1}, [%2];" : "=r"(v.x), "=r"(v.y) : "l"(a) : "memory");
  return v;
}
__device__ __forceinline__ void ldsm4(uint32_t* r, uint32_t a) {
  asm volatile("ldmatrix.sync.aligned.m8n8.x4.shared.b16 {%0, %1, %2, %3}, [%4];"
               : "=r"(r[0]), "=r"(r[1]), "=r"(r[2]), "=r"(r[3]) : "r"(a) : "memory");
}
__device__ __forceinline__ void ldsm4t(uint32_t* r, uint32_t a) {
  asm volatile("ldmatrix.sync.aligned.m8n8.x4.trans.shared.b16 {%0, %1, %2, %3}, [%4];"
               : "=r"(r[0]), "=r"(r[1]), "=r"(r[2]), "=r"(r[3]) : "r"(a) : "memory");
}
__device__ __forceinline__ uint2 lds64(uint32_t a) {
  uint2 v;
  asm volatile("ld.shared.v2.u32 {%0, %1}, [%2];" : "=r"(v.x), "=r"(v.y) : "r"(a) : "memory");
  return v;
}
__device__ __forceinline__ uint4 lds128(uint32_t a) {
  uint4 v;
  asm volatile("ld.shared.v4.u32 {%0, %1, %2, %3}, [%4];" : "=r"(v.x), "=r"(v.y), "=r"(v.z), "=r"(v.w) : "r"(a) : "memory");
  return v;
}
__device__ __forceinline__ void sts128(uint32_t a, uint32_t x, uint32_t y, uint32_t z, uint32_t w) {
  asm volatile("st.shared.v4.u32 [%0], {%1, %2, %3, %4};" ::"r"(a), "r"(x), "r"(y), "r"(z), "r"(w) : "memory");
}
__device__ __forceinline__ void stsm4(uint32_t a, const uint32_t* r) {
  asm volatile("stmatrix.sync.aligned.m8n8.x4.shared.b16 [%0], {%1, %2, %3, %4};" ::"r"(a), "r"(r[0]), "r"(r[1]), "r"(r[2]), "r"(r[3]) : "memory");
}
__device__ __forceinline__ void stsm4t(uint32_t a, const uint32_t* r) {
  asm volatile("stmatrix.sync.aligned.m8n8.x4.trans.shared.b16 [%0], {%1, %2, %3, %4};" ::"r"(a), "r"(r[0]), "r"(r[1]), "r"(r[2]), "r"(r[3]) : "memory");
}
__device__ __forceinline__ uint32_t pack2(float lo, float hi) {
  uint32_t r;
  asm("cvt.rn.bf16x2.f32 %0, %1, %2;" : "=r"(r) : "f"(hi), "f"(lo));
  return r;
}
__device__ __forceinline__ uint32_t movm(uint32_t a) {
  uint32_t d;
  asm volatile("movmatrix.sync.aligned.m8n8.trans.b16 %0, %1;" : "=r"(d) : "r"(a));
  return d;
}
__device__ __forceinline__ uint32_t bmul(uint32_t a, uint32_t b) {
  uint32_t d;
  asm("mul.rn.bf16x2 %0, %1, %2;" : "=r"(d) : "r"(a), "r"(b));
  return d;
}
__device__ __forceinline__ uint32_t badd(uint32_t a, uint32_t b) {
  uint32_t d;
  asm("add.rn.bf16x2 %0, %1, %2;" : "=r"(d) : "r"(a), "r"(b));
  return d;
}
__device__ __forceinline__ uint32_t bfma(uint32_t a, uint32_t b, uint32_t c) {
  uint32_t d;
  asm("fma.rn.bf16x2 %0, %1, %2, %3;" : "=r"(d) : "r"(a), "r"(b), "r"(c));
  return d;
}
__device__ __forceinline__ float bf_lo(uint32_t x) { return __uint_as_float(x << 16); }
__device__ __forceinline__ float bf_hi(uint32_t x) { return __uint_as_float(x & 0xFFFF0000u); }
__device__ __forceinline__ float ex2(float x) {
  float y;
  asm("ex2.approx.ftz.f32 %0, %1;" : "=f"(y) : "f"(x));
  return y;
}
__device__ __forceinline__ float rcp(float x) {
  float y;
  asm("rcp.approx.ftz.f32 %0, %1;" : "=f"(y) : "f"(x));
  return y;
}
__device__ __forceinline__ void mma16816(float* d, uint32_t a0, uint32_t a1, uint32_t a2, uint32_t a3, uint32_t b0, uint32_t b1) {
  asm volatile("mma.sync.aligned.m16n8k16.row.col.f32.bf16.bf16.f32 {%0, %1, %2, %3}, {%4, %5, %6, %7}, {%8, %9}, {%0, %1, %2, %3};"
               : "+f"(d[0]), "+f"(d[1]), "+f"(d[2]), "+f"(d[3])
               : "r"(a0), "r"(a1), "r"(a2), "r"(a3), "r"(b0), "r"(b1));
}
__device__ __forceinline__ void mma1688(float* d, uint32_t a0, uint32_t a1, uint32_t b0) {
  asm volatile("mma.sync.aligned.m16n8k8.row.col.f32.bf16.bf16.f32 {%0, %1, %2, %3}, {%4, %5}, {%6}, {%0, %1, %2, %3};"
               : "+f"(d[0]), "+f"(d[1]), "+f"(d[2]), "+f"(d[3])
               : "r"(a0), "r"(a1), "r"(b0));
}

template <int N> struct WgRS;
template <int N> struct WgSST;
template <> struct WgRS<32> {
  template <uint32_t HB>
  static __device__ __forceinline__ void mma(float* d, const uint32_t* a, uint32_t db) {
    asm volatile("{\n.reg .pred p;\n.reg .b64 db;\nsetp.ne.b32 p, %22, 0;\n"
      "mov.b64 db, {%20, %21};\n"
      "wgmma.mma_async.sync.aligned.m64n32k16.f32.bf16.bf16 {"
      "%0, %1, %2, %3, %4, %5, %6, %7, %8, %9, %10, %11, %12, %13, %14, %15"
      "}, {%16, %17, %18, %19}, db, p, 1, 1, 1;\n}\n"
      : "+f"(d[0]), "+f"(d[1]), "+f"(d[2]), "+f"(d[3]), "+f"(d[4]), "+f"(d[5]), "+f"(d[6]), "+f"(d[7]),
        "+f"(d[8]), "+f"(d[9]), "+f"(d[10]), "+f"(d[11]), "+f"(d[12]), "+f"(d[13]), "+f"(d[14]), "+f"(d[15])
      : "r"(a[0]), "r"(a[1]), "r"(a[2]), "r"(a[3]), "r"(db), "n"(HB), "n"(1));
  }
  template <uint32_t HB>
  static __device__ __forceinline__ void set(float* d, const uint32_t* a, uint32_t db) {
    asm volatile("{\n.reg .pred p;\n.reg .b64 db;\nsetp.ne.b32 p, %22, 0;\n"
      "mov.b64 db, {%20, %21};\n"
      "wgmma.mma_async.sync.aligned.m64n32k16.f32.bf16.bf16 {"
      "%0, %1, %2, %3, %4, %5, %6, %7, %8, %9, %10, %11, %12, %13, %14, %15"
      "}, {%16, %17, %18, %19}, db, p, 1, 1, 1;\n}\n"
      : "=f"(d[0]), "=f"(d[1]), "=f"(d[2]), "=f"(d[3]), "=f"(d[4]), "=f"(d[5]), "=f"(d[6]), "=f"(d[7]),
        "=f"(d[8]), "=f"(d[9]), "=f"(d[10]), "=f"(d[11]), "=f"(d[12]), "=f"(d[13]), "=f"(d[14]), "=f"(d[15])
      : "r"(a[0]), "r"(a[1]), "r"(a[2]), "r"(a[3]), "r"(db), "n"(HB), "n"(0));
  }
};
template <> struct WgRS<64> {
  template <uint32_t HB>
  static __device__ __forceinline__ void mma(float* d, const uint32_t* a, uint32_t db) {
    asm volatile("{\n.reg .pred p;\n.reg .b64 db;\nsetp.ne.b32 p, %38, 0;\n"
      "mov.b64 db, {%36, %37};\n"
      "wgmma.mma_async.sync.aligned.m64n64k16.f32.bf16.bf16 {"
      "%0, %1, %2, %3, %4, %5, %6, %7, %8, %9, %10, %11, %12, %13, %14, %15, "
      "%16, %17, %18, %19, %20, %21, %22, %23, %24, %25, %26, %27, %28, %29, %30, %31"
      "}, {%32, %33, %34, %35}, db, p, 1, 1, 1;\n}\n"
      : "+f"(d[0]), "+f"(d[1]), "+f"(d[2]), "+f"(d[3]), "+f"(d[4]), "+f"(d[5]), "+f"(d[6]), "+f"(d[7]),
        "+f"(d[8]), "+f"(d[9]), "+f"(d[10]), "+f"(d[11]), "+f"(d[12]), "+f"(d[13]), "+f"(d[14]), "+f"(d[15]),
        "+f"(d[16]), "+f"(d[17]), "+f"(d[18]), "+f"(d[19]), "+f"(d[20]), "+f"(d[21]), "+f"(d[22]), "+f"(d[23]),
        "+f"(d[24]), "+f"(d[25]), "+f"(d[26]), "+f"(d[27]), "+f"(d[28]), "+f"(d[29]), "+f"(d[30]), "+f"(d[31])
      : "r"(a[0]), "r"(a[1]), "r"(a[2]), "r"(a[3]), "r"(db), "n"(HB), "n"(1));
  }
  template <uint32_t HB>
  static __device__ __forceinline__ void set(float* d, const uint32_t* a, uint32_t db) {
    asm volatile("{\n.reg .pred p;\n.reg .b64 db;\nsetp.ne.b32 p, %38, 0;\n"
      "mov.b64 db, {%36, %37};\n"
      "wgmma.mma_async.sync.aligned.m64n64k16.f32.bf16.bf16 {"
      "%0, %1, %2, %3, %4, %5, %6, %7, %8, %9, %10, %11, %12, %13, %14, %15, "
      "%16, %17, %18, %19, %20, %21, %22, %23, %24, %25, %26, %27, %28, %29, %30, %31"
      "}, {%32, %33, %34, %35}, db, p, 1, 1, 1;\n}\n"
      : "=f"(d[0]), "=f"(d[1]), "=f"(d[2]), "=f"(d[3]), "=f"(d[4]), "=f"(d[5]), "=f"(d[6]), "=f"(d[7]),
        "=f"(d[8]), "=f"(d[9]), "=f"(d[10]), "=f"(d[11]), "=f"(d[12]), "=f"(d[13]), "=f"(d[14]), "=f"(d[15]),
        "=f"(d[16]), "=f"(d[17]), "=f"(d[18]), "=f"(d[19]), "=f"(d[20]), "=f"(d[21]), "=f"(d[22]), "=f"(d[23]),
        "=f"(d[24]), "=f"(d[25]), "=f"(d[26]), "=f"(d[27]), "=f"(d[28]), "=f"(d[29]), "=f"(d[30]), "=f"(d[31])
      : "r"(a[0]), "r"(a[1]), "r"(a[2]), "r"(a[3]), "r"(db), "n"(HB), "n"(0));
  }
};
template <> struct WgSST<48> {
  template <uint32_t HA, uint32_t HB>
  static __device__ __forceinline__ void mma(float* d, uint32_t da, uint32_t db, int sc) {
    asm volatile("{\n.reg .pred p;\n.reg .b64 da, db;\nsetp.ne.b32 p, %28, 0;\n"
      "mov.b64 da, {%24, %25};\nmov.b64 db, {%26, %27};\n"
      "wgmma.mma_async.sync.aligned.m64n48k16.f32.bf16.bf16 {"
      "%0, %1, %2, %3, %4, %5, %6, %7, %8, %9, %10, %11, %12, %13, %14, %15, "
      "%16, %17, %18, %19, %20, %21, %22, %23"
      "}, da, db, p, 1, 1, 0, 1;\n}\n"
      : "+f"(d[0]), "+f"(d[1]), "+f"(d[2]), "+f"(d[3]), "+f"(d[4]), "+f"(d[5]), "+f"(d[6]), "+f"(d[7]),
        "+f"(d[8]), "+f"(d[9]), "+f"(d[10]), "+f"(d[11]), "+f"(d[12]), "+f"(d[13]), "+f"(d[14]), "+f"(d[15]),
        "+f"(d[16]), "+f"(d[17]), "+f"(d[18]), "+f"(d[19]), "+f"(d[20]), "+f"(d[21]), "+f"(d[22]), "+f"(d[23])
      : "r"(da), "n"(HA), "r"(db), "n"(HB), "r"(sc));
  }
};
template <> struct WgSST<80> {
  template <uint32_t HA, uint32_t HB>
  static __device__ __forceinline__ void mma(float* d, uint32_t da, uint32_t db, int sc) {
    asm volatile("{\n.reg .pred p;\n.reg .b64 da, db;\nsetp.ne.b32 p, %44, 0;\n"
      "mov.b64 da, {%40, %41};\nmov.b64 db, {%42, %43};\n"
      "wgmma.mma_async.sync.aligned.m64n80k16.f32.bf16.bf16 {"
      "%0, %1, %2, %3, %4, %5, %6, %7, %8, %9, %10, %11, %12, %13, %14, %15, "
      "%16, %17, %18, %19, %20, %21, %22, %23, %24, %25, %26, %27, %28, %29, %30, %31, "
      "%32, %33, %34, %35, %36, %37, %38, %39"
      "}, da, db, p, 1, 1, 0, 1;\n}\n"
      : "+f"(d[0]), "+f"(d[1]), "+f"(d[2]), "+f"(d[3]), "+f"(d[4]), "+f"(d[5]), "+f"(d[6]), "+f"(d[7]),
        "+f"(d[8]), "+f"(d[9]), "+f"(d[10]), "+f"(d[11]), "+f"(d[12]), "+f"(d[13]), "+f"(d[14]), "+f"(d[15]),
        "+f"(d[16]), "+f"(d[17]), "+f"(d[18]), "+f"(d[19]), "+f"(d[20]), "+f"(d[21]), "+f"(d[22]), "+f"(d[23]),
        "+f"(d[24]), "+f"(d[25]), "+f"(d[26]), "+f"(d[27]), "+f"(d[28]), "+f"(d[29]), "+f"(d[30]), "+f"(d[31]),
        "+f"(d[32]), "+f"(d[33]), "+f"(d[34]), "+f"(d[35]), "+f"(d[36]), "+f"(d[37]), "+f"(d[38]), "+f"(d[39])
      : "r"(da), "n"(HA), "r"(db), "n"(HB), "r"(sc));
  }
};
template <> struct WgSST<192> {
  template <uint32_t HA, uint32_t HB>
  static __device__ __forceinline__ void mma(float* d, uint32_t da, uint32_t db, int sc) {
    asm volatile("{\n.reg .pred p;\n.reg .b64 da, db;\nsetp.ne.b32 p, %100, 0;\n"
      "mov.b64 da, {%96, %97};\nmov.b64 db, {%98, %99};\n"
      "wgmma.mma_async.sync.aligned.m64n192k16.f32.bf16.bf16 {"
      "%0, %1, %2, %3, %4, %5, %6, %7, %8, %9, %10, %11, %12, %13, %14, %15, "
      "%16, %17, %18, %19, %20, %21, %22, %23, %24, %25, %26, %27, %28, %29, %30, %31, "
      "%32, %33, %34, %35, %36, %37, %38, %39, %40, %41, %42, %43, %44, %45, %46, %47, "
      "%48, %49, %50, %51, %52, %53, %54, %55, %56, %57, %58, %59, %60, %61, %62, %63, "
      "%64, %65, %66, %67, %68, %69, %70, %71, %72, %73, %74, %75, %76, %77, %78, %79, "
      "%80, %81, %82, %83, %84, %85, %86, %87, %88, %89, %90, %91, %92, %93, %94, %95"
      "}, da, db, p, 1, 1, 0, 1;\n}\n"
      : "+f"(d[0]), "+f"(d[1]), "+f"(d[2]), "+f"(d[3]), "+f"(d[4]), "+f"(d[5]), "+f"(d[6]), "+f"(d[7]),
        "+f"(d[8]), "+f"(d[9]), "+f"(d[10]), "+f"(d[11]), "+f"(d[12]), "+f"(d[13]), "+f"(d[14]), "+f"(d[15]),
        "+f"(d[16]), "+f"(d[17]), "+f"(d[18]), "+f"(d[19]), "+f"(d[20]), "+f"(d[21]), "+f"(d[22]), "+f"(d[23]),
        "+f"(d[24]), "+f"(d[25]), "+f"(d[26]), "+f"(d[27]), "+f"(d[28]), "+f"(d[29]), "+f"(d[30]), "+f"(d[31]),
        "+f"(d[32]), "+f"(d[33]), "+f"(d[34]), "+f"(d[35]), "+f"(d[36]), "+f"(d[37]), "+f"(d[38]), "+f"(d[39]),
        "+f"(d[40]), "+f"(d[41]), "+f"(d[42]), "+f"(d[43]), "+f"(d[44]), "+f"(d[45]), "+f"(d[46]), "+f"(d[47]),
        "+f"(d[48]), "+f"(d[49]), "+f"(d[50]), "+f"(d[51]), "+f"(d[52]), "+f"(d[53]), "+f"(d[54]), "+f"(d[55]),
        "+f"(d[56]), "+f"(d[57]), "+f"(d[58]), "+f"(d[59]), "+f"(d[60]), "+f"(d[61]), "+f"(d[62]), "+f"(d[63]),
        "+f"(d[64]), "+f"(d[65]), "+f"(d[66]), "+f"(d[67]), "+f"(d[68]), "+f"(d[69]), "+f"(d[70]), "+f"(d[71]),
        "+f"(d[72]), "+f"(d[73]), "+f"(d[74]), "+f"(d[75]), "+f"(d[76]), "+f"(d[77]), "+f"(d[78]), "+f"(d[79]),
        "+f"(d[80]), "+f"(d[81]), "+f"(d[82]), "+f"(d[83]), "+f"(d[84]), "+f"(d[85]), "+f"(d[86]), "+f"(d[87]),
        "+f"(d[88]), "+f"(d[89]), "+f"(d[90]), "+f"(d[91]), "+f"(d[92]), "+f"(d[93]), "+f"(d[94]), "+f"(d[95])
      : "r"(da), "n"(HA), "r"(db), "n"(HB), "r"(sc));
  }
};

struct FftConst {
  uint32_t f[2][4], fi[4][4];
  uint32_t ta[2][2], tb[2][2];
};
__device__ __forceinline__ void cis(int m, float scale, float& c, float& s) {
  const float a = (float)m * (-6.283185307179586f * scale);
  c = __cosf(a);
  s = __sinf(a);
}
__device__ __forceinline__ void fft_tables(uint32_t (&v)[12], int tw) {
  const int row = tw >> 2, ch = tw & 3;
#pragma unroll
  for (int i = 0; i < 4; i++) {
    float c[2], s[2], x[2];
#pragma unroll
    for (int e = 0; e < 2; e++) {
      cis((((32 * (8 * ch + 2 * i + e) + 15) * (4 * row - 63) + 2048) & 4095) - 2048, 1.f / 4096, c[e], s[e]);
      float gc, gs;
      cis((((row & 15) * (8 * (ch & 1) + 2 * i + e) + 8) & 15) - 8, 1.f / 16, gc, gs);
      x[e] = (row >> 4) == (ch >> 1) ? gc : (ch >> 1) ? gs : -gs;
    }
    v[i] = pack2(c[0] * 0.125f, c[1] * 0.125f);
    v[4 + i] = pack2(s[0] * 0.125f, s[1] * 0.125f);
    v[8 + i] = pack2(x[0], x[1]);
  }
#pragma unroll
  for (int i = 0; i < 12; i++) asm volatile("" : "+r"(v[i]));
}
__device__ __forceinline__ void fft_tables_store(const uint32_t (&v)[12], uint32_t sb, int tw) {
  const int row = tw >> 2;
  const uint32_t x = ((tw ^ (row >> 1)) & 3) << 4, a = sb + OFF_FT + (16 * (row >> 3) + (row & 7)) * 64 + x;
  sts128(a, v[0], v[1], v[2], v[3]);
  sts128(a + 512, v[4], v[5], v[6], v[7]);
  sts128(sb + OFF_GT + row * 64 + x, v[8], v[9], v[10], v[11]);
}
__device__ __forceinline__ void fft_twiddles(uint32_t (&v)[2], int tw) {
  float a[2], s[2];
#pragma unroll
  for (int i = 0; i < 2; i++) {
    float c;
    cis((2 * (2 * (tw & 3) + i) - 15) * (4 * (tw >> 2) - 63), 1.f / 4096, c, s[i]);
    a[i] = __fdividef(-s[i], 1.f + c);
  }
  v[0] = pack2(a[0], a[1]);
  v[1] = pack2(s[0], s[1]);
  asm volatile("" : "+r"(v[0]), "+r"(v[1]));
}
__device__ __forceinline__ void fft_matrices(FftConst& k, uint32_t sb, int w, int lane) {
  const uint32_t x = (lane >> 1) & 3;
  const uint2 t0 = lds64(sb + OFF_TT + 256 * w + 8 * lane), t1 = lds64(sb + OFF_TT + 256 * w + 8 * (lane ^ 3));
  k.ta[0][0] = t0.x;
  k.tb[0][0] = t0.y;
  k.ta[1][1] = __byte_perm(t1.x, 0, 0x1032);
  k.tb[1][1] = __byte_perm(t1.y, 0, 0x1032);
#pragma unroll
  for (int j = 0; j < 2; j++) {
    k.ta[1 - j][j] = k.ta[j][j] ^ 0x80008000u;
    k.tb[1 - j][j] = k.tb[j][j] ^ 0x80008000u;
    asm volatile("" : "+r"(k.ta[0][j]), "+r"(k.tb[0][j]), "+r"(k.ta[1][j]), "+r"(k.tb[1][j]));
  }
#pragma unroll
  for (int i = 0; i < 2; i++) {
    ldsm4(k.f[i], sb + OFF_FT + (16 * w + (lane & 15)) * 64 + (((2 * i + (lane >> 4)) ^ x) << 4));
    ldsm4t(k.fi[i], sb + OFF_FT + (32 * i + lane) * 64 + ((w ^ x) << 4));
#pragma unroll
    for (int j = 0; j < 4; j++) {
      k.fi[2 + i][j] = (j & 1) ? k.fi[i][j - 1] ^ 0x80008000u : k.fi[i][j + 1];
      asm volatile("" : "+r"(k.fi[2 + i][j]));
    }
  }
}
__device__ __forceinline__ void rot(uint32_t& x, uint32_t& y, uint32_t a, uint32_t b) {
  x = bfma(a, y, x);
  y = bfma(b, x, y);
  x = bfma(a, y, x);
}
__device__ __forceinline__ void twiddle_fwd(uint32_t (&a)[4][4], float* d, const FftConst& k) {
#pragma unroll
  for (int q = 0; q < 4; q++)
#pragma unroll
    for (int j = 0; j < 2; j++) {
      const float* x = d + 8 * q + 4 * j;
      uint32_t re = pack2(x[0], x[1]), im = pack2(x[2], x[3]);
      rot(re, im, k.ta[0][j], k.tb[0][j]);
      a[q & 2][2 * j + (q & 1)] = re;
      a[(q & 2) + 1][2 * j + (q & 1)] = im;
    }
}
__device__ __forceinline__ void g_step(float* d, const uint32_t (&a)[4][4], uint32_t dre, uint32_t dim) {
  WgRS<32>::set<HI_SW64>(d, a[0], dre);
  WgRS<32>::set<HI_SW64>(d + 16, a[2], dre);
  WgRS<32>::mma<HI_SW64>(d, a[1], dim);
  WgRS<32>::mma<HI_SW64>(d + 16, a[3], dim);
  wg_commit();
}

__device__ __forceinline__ void conv_channel(const FftConst& k, uint32_t sb, int c, int wg, int w, int lane) {
  const uint32_t cb = sb + off_ch(c), bars = sb + OFF_BAR;
  const uint32_t du = desc_lo(cb, 1024), dg = desc_lo(sb + OFF_GT, 16), dz = desc_lo(cb + U_BYTES, 16);
  float U[32], H[32];
  uint32_t a[4][4], e[4][4];
  const float dv = __uint_as_float(lds32(sb + OFF_D + 4 * c));
  wg_fence();
  WgRS<64>::set<HI_SW32>(H, k.f[0], du + 256);
  WgRS<64>::mma<HI_SW32>(H, k.f[1], du + 256 + 32);
  wg_commit();
  wg_wait<0>();
  pin<32>(H);
  twiddle_fwd(a, H, k);
  if (ATT_GATE) mbar_wait(bars + 8 * (ATT_GATE == 1 ? B_ATTN : B_ATT2), 0);
  mbar_wait(bars + 8 * (B_U + (c < 3 ? c : 3)), 0);
  TSM(w == 0 && c < 3, 7 + wg);
  wg_fence();
  WgRS<64>::set<HI_SW32>(U, k.f[0], du);
  WgRS<64>::mma<HI_SW32>(U, k.f[1], du + 32);
  wg_commit();
  g_step(H, a, dg, dg + 64);
  wg_wait<1>();
  pin<32>(U);
  twiddle_fwd(e, U, k);
  wg_fence();
  g_step(U, e, dg, dg + 64);
  wg_wait<0>();
  pin<32>(U);
  pin<32>(H);
#pragma unroll
  for (int j = 0; j < 2; j++) {
    float pr[4][2], pi[4][2];
#pragma unroll
    for (int x = 0; x < 2; x++) {
      H[4 * j + x] += dv;
#pragma unroll
      for (int m = 0; m < 4; m++) {
#pragma unroll
        for (int q = 0; q <= m; q++) {
          const int ih = 16 * (q >> 1) + 2 * (q & 1) + 4 * j + x, iu = 16 * ((m - q) >> 1) + 2 * ((m - q) & 1) + 4 * j + x;
          pr[m][x] = q ? fmaf(H[ih], U[iu], pr[m][x]) : H[ih] * U[iu];
          pi[m][x] = q ? fmaf(H[ih], U[iu + 8], pi[m][x]) : H[ih] * U[iu + 8];
          pr[m][x] = fmaf(-H[ih + 8], U[iu + 8], pr[m][x]);
          pi[m][x] = fmaf(H[ih + 8], U[iu], pi[m][x]);
        }
      }
    }
#pragma unroll
    for (int m = 0; m < 4; m++) {
      a[m & 2][2 * j + (m & 1)] = pack2(pr[m][0], pr[m][1]);
      a[(m & 2) + 1][2 * j + (m & 1)] = pack2(pi[m][0], pi[m][1]);
    }
  }
  wg_fence();
  g_step(U, a, dg + 64, dg);
  const uint32_t za = cb + U_BYTES + (8 * w + (lane & 7)) * 128 + (((lane >> 3) ^ (lane & 7)) << 4);
  const uint32_t ya = cb + (lane >> 4) * 1024 + (8 * w + (lane & 7)) * 32 + ((((lane >> 3) ^ (lane >> 2)) & 1) << 4);
  wg_sync(1 + wg);
  wg_wait<0>();
  pin<32>(U);
  TSIF(w == 0, 80 + c);
#pragma unroll
  for (int p = 0; p < 2; p++) {
#pragma unroll
    for (int i = 0; i < 4; i++) {
      const int j = i & 1;
      const float* x = U + 16 * p + 4 * j + (i & 2);
      e[p][i] = pack2(x[8], x[9]);
      e[2 + p][i] = pack2(x[0], x[1]);
      rot(e[p][i], e[2 + p][i], k.ta[1][j], k.tb[1][j]);
    }
    stsm4(za ^ (64 * p), e[p]);
    stsm4((za ^ (64 * p)) + 4096, e[2 + p]);
  }
  fence_async_smem();
  wg_sync(1 + wg);
  wg_fence();
  WgRS<64>::set<HI_SW128>(H, k.fi[0], dz);
#pragma unroll
  for (int ks = 1; ks < 4; ks++) WgRS<64>::mma<HI_SW128>(H, k.fi[ks], dz + 128 * ks);
  wg_commit();
  if (WO_FAST) mbar_wait(bars + 8 * B_ATTN, 0);
  wg_wait<0>();
  pin<32>(H);
  TSIF(w == 0, 88 + c);
#pragma unroll
  for (int j = 0; j < 8; j++)
    a[j >> 2][j & 3] = j < 2 ? pack2(H[4 * j], H[4 * j + 1]) : pack2(H[4 * j] + H[4 * j - 6], H[4 * j + 1] + H[4 * j - 5]);
  stsm4(ya, a[0]);
  stsm4(ya + 2048, a[1]);
  fence_async_smem();
  __syncwarp();
}

__device__ __forceinline__ void prep_slab(uint4* res, const uint2* sw, uint32_t sb, int slab, int w, int lane) {
  const int t = lane & 3, tp = (lane & 7) >> 1, pos = 8 * tp + 2 * (((lane >> 3) + tp) & 3) + (lane & 1);
  const uint32_t base = sb + OFF_KVS + slab * KVS_BYTES + pos * 128;
  uint32_t kk[2][4][4], vv[2][4];
  mbar_wait(sb + OFF_BAR + 8 * (B_KV + slab), 0);
#pragma unroll
  for (int h = 0; h < 2; h++) {
#pragma unroll
    for (int j = 0; j < 4; j++) {
      const uint32_t a = base + 128 * j;
      ldsm4t(kk[h][j], a + (((w + 4 * h) ^ ((a >> 7) & 7)) << 4));
    }
    const uint32_t a = base + KVS_V;
    ldsm4t(vv[h], a + (((w + 4 * h) ^ ((a >> 7) & 7)) << 4));
  }
#pragma unroll
  for (int h = 0; h < 2; h++) {
    uint32_t (&k)[4][4] = kk[h];
    uint32_t (&v)[4] = vv[h];
    const uint32_t w0 = __byte_perm(sw[h].x, 0, 0x1010), w1 = __byte_perm(sw[h].x, 0, 0x3232);
    const uint32_t w2 = __byte_perm(sw[h].y, 0, 0x1010), w3 = __byte_perm(sw[h].y, 0, 0x3232);
#pragma unroll
    for (int m = 0; m < 4; m++)
      v[m] = bmul(badd(badd(badd(bmul(k[0][m], w3), bmul(k[1][m], w2)), bmul(k[2][m], w1)), bmul(k[3][m], w0)), v[m]);
    uint32_t a[4];
#pragma unroll
    for (int m = 0; m < 4; m++) a[m] = (t & 1) ? v[(m + 3) & 3] : v[m];
    res[h] = (t & 2) ? make_uint4(a[2], a[3], a[0], a[1]) : make_uint4(a[0], a[1], a[2], a[3]);
  }
}

__device__ __forceinline__ void prep_gate(const Params& p, uint32_t sb, int b, int w, int lane) {
  uint2 gw[5], x[4][5];
#pragma unroll
  for (int j = 0; j < 5; j++) gw[j] = ldg64(reinterpret_cast<const uint2*>(p.gate_w) + lane + 32 * j);
#pragma unroll
  for (int i = 0; i < 4; i++)
#pragma unroll
    for (int j = 0; j < 5; j++)
      x[i][j] = ldg64(reinterpret_cast<const uint2*>(p.q) + (16 * b + 4 * w + i) * (DIM / 4) + lane + 32 * j);
  float s[4];
#pragma unroll
  for (int i = 0; i < 4; i++) {
    s[i] = 0.f;
#pragma unroll
    for (int j = 0; j < 5; j++) {
      const uint32_t m0 = bmul(x[i][j].x, gw[j].x), m1 = bmul(x[i][j].y, gw[j].y);
      s[i] += (bf_lo(m0) + bf_hi(m0)) + (bf_lo(m1) + bf_hi(m1));
    }
  }
  const bool h = lane & 16, q = lane & 8;
  const float a = (h ? s[2] : s[0]) + __shfl_xor_sync(0xffffffffu, h ? s[0] : s[2], 16);
  const float c = (h ? s[3] : s[1]) + __shfl_xor_sync(0xffffffffu, h ? s[1] : s[3], 16);
  float z = (q ? c : a) + __shfl_xor_sync(0xffffffffu, q ? a : c, 8);
#pragma unroll
  for (int o = 4; o > 0; o >>= 1) z += __shfl_xor_sync(0xffffffffu, z, o);
  z = bf_lo(pack2(z, 0.f));
  z = bf_lo(pack2(__fdividef(1.f, 1.f + __expf(-z)), 0.f));
  if (G_TMA) {
    mbar_wait(sb + OFF_BAR + 8 * B_S3, 0);
    if ((lane & 7) == 0) asm volatile("st.shared.f32 [%0], %1;" ::"r"(sb + OFF_GATE + 64 * (b & 7) + 16 * w + (lane >> 1)), "f"(z) : "memory");
    fence_async_smem();
  } else if ((lane & 7) == 0) {
    g_gate[16 * b + 4 * w + (lane >> 3)] = z;
  }
}

__device__ __forceinline__ uint32_t bmax(uint32_t a, uint32_t b) {
  uint32_t d;
  asm("max.bf16x2 %0, %1, %2;" : "=r"(d) : "r"(a), "r"(b));
  return d;
}
__device__ __forceinline__ void softmax_two(const float (&l)[2][2], uint32_t& p0, uint32_t& p1) {
  constexpr float kScale = 0.22360679774997896f, kLog2e = 1.4426950408889634f;
  const uint32_t r0 = pack2(l[0][0], l[1][0]), r1 = pack2(l[0][1], l[1][1]);
  const uint32_t x0 = pack2(bf_lo(r0) * kScale, bf_hi(r0) * kScale), x1 = pack2(bf_lo(r1) * kScale, bf_hi(r1) * kScale);
  uint32_t m = bmax(x0, x1);
  m = bmax(m, __shfl_xor_sync(0xffffffffu, m, 1));
  m = bmax(m, __shfl_xor_sync(0xffffffffu, m, 2));
  const float m0 = bf_lo(m) * kLog2e, m1 = bf_hi(m) * kLog2e;
  p0 = pack2(ex2(bf_lo(x0) * kLog2e - m0), ex2(bf_lo(x1) * kLog2e - m0));
  p1 = pack2(ex2(bf_hi(x0) * kLog2e - m1), ex2(bf_hi(x1) * kLog2e - m1));
}

__device__ __forceinline__ void halo_read(uint32_t (&kpv)[10], uint32_t (&vpv)[10], uint32_t (&tg)[7], const uint4* hp) {
#pragma unroll
  for (int j = 0; j < 7; j++) {
    uint32_t x0, x1, x2;
    asm volatile("ld.relaxed.gpu.global.v4.u32 {%0, %1, %2, %3}, [%4];"
                 : "=r"(x0), "=r"(x1), "=r"(x2), "=r"(tg[j]) : "l"(hp + 32 * j) : "memory");
    if (j < 4) kpv[3 * j] = x0; else vpv[3 * j - 10] = x0;
    if (j < 3) kpv[3 * j + 1] = x1; else vpv[3 * j - 9] = x1;
    if (j < 3) kpv[3 * j + 2] = x2; else if (j < 6) vpv[3 * j - 8] = x2;
  }
}

template <int ROT>
__device__ __forceinline__ void pack_qkv(const float* acc, uint32_t (&qlo)[10], uint32_t (&qhi)[10], uint32_t (&klo)[10],
                                         uint32_t (&khi)[10], uint32_t (&vlo)[10], uint32_t (&vhi)[10]) {
#pragma unroll
  for (int j = 0; j < 10; j++) {
    const int x = (j + ROT) % 10, tq = x < 8 ? x : 16 + x, tk = x < 8 ? 8 + x : 18 + x, tv = x < 8 ? 16 + x : 20 + x;
    khi[j] = pack2(acc[4 * tk + 2], acc[4 * tk + 3]);
    vhi[j] = movm(pack2(acc[4 * tv + 2], acc[4 * tv + 3]));
    qlo[j] = pack2(acc[4 * tq], acc[4 * tq + 1]);
    qhi[j] = pack2(acc[4 * tq + 2], acc[4 * tq + 3]);
    klo[j] = pack2(acc[4 * tk], acc[4 * tk + 1]);
    vlo[j] = pack2(acc[4 * tv], acc[4 * tv + 1]);
    asm volatile("" : "+r"(khi[j]), "+r"(qlo[j]), "+r"(qhi[j]), "+r"(klo[j]), "+r"(vlo[j]));
  }
}

template <int ROT> __device__ __forceinline__ void halo_send(const float* acc, uint4* ho, uint32_t tag) {
#pragma unroll
  for (int j = 0; j < 7; j++) {
    uint32_t x[3];
#pragma unroll
    for (int e = 0; e < 3; e++) {
      const int i = 3 * j + e, y = (i % 10 + ROT) % 10, tk = y < 8 ? 8 + y : 18 + y, tv = y < 8 ? 16 + y : 20 + y;
      x[e] = i < 10 ? pack2(acc[4 * tk + 2], acc[4 * tk + 3]) : i < 20 ? movm(pack2(acc[4 * tv + 2], acc[4 * tv + 3])) : 0u;
    }
    asm volatile("st.relaxed.gpu.global.v4.u32 [%0], {%1, %2, %3, %4};" ::"l"(ho + 32 * j), "r"(x[0]), "r"(x[1]), "r"(x[2]), "r"(tag) : "memory");
  }
}

__device__ __forceinline__ void attention(float* acc, uint32_t sb, int b, int par, int w, int lane, uint32_t tag, uint32_t zero) {
  const int g = lane >> 2, t = lane & 3;
  uint32_t klo[10], khi[10], vlo[10], vhi[10], qlo[10], qhi[10], kpv[10], vpv[10];
  if (HALO_FIRST && w == 3 && b < NCTA - 8) {
    uint4* ho = g_halo + (b * 2 + par) * 224 + lane;
    if (tail_first(b & 7)) halo_send<8>(acc, ho, tag);
    else halo_send<0>(acc, ho, tag);
    TSIF(par == 0, 76);
    pin<120>(acc);
  }
  if (tail_first(b & 7)) pack_qkv<8>(acc, qlo, qhi, klo, khi, vlo, vhi);
  else pack_qkv<0>(acc, qlo, qhi, klo, khi, vlo, vhi);
  const uint32_t xa = sb + OFF_KVX + (par * 3) * 2560 + lane * 16;
  if (w < 3) {
    sts128(xa + w * 2560, khi[0], khi[1], khi[2], khi[3]);
    sts128(xa + w * 2560 + 512, khi[4], khi[5], khi[6], khi[7]);
    sts128(xa + w * 2560 + 1024, khi[8], khi[9], vhi[0], vhi[1]);
    sts128(xa + w * 2560 + 1536, vhi[2], vhi[3], vhi[4], vhi[5]);
    sts128(xa + w * 2560 + 2048, vhi[6], vhi[7], vhi[8], vhi[9]);
  } else if (!HALO_FIRST && b < NCTA - 8) {
    uint4* ho = g_halo + (b * 2 + par) * 224 + lane;
#pragma unroll
    for (int j = 0; j < 7; j++) {
      const uint32_t x0 = j < 4 ? khi[3 * j] : vhi[3 * j - 10], x1 = j < 3 ? khi[3 * j + 1] : vhi[3 * j - 9];
      const uint32_t x2 = j < 3 ? khi[3 * j + 2] : j < 6 ? vhi[3 * j - 8] : 0u;
      asm volatile("st.relaxed.gpu.global.v4.u32 [%0], {%1, %2, %3, %4};" ::"l"(ho + 32 * j), "r"(x0), "r"(x1), "r"(x2), "r"(tag) : "memory");
    }
  }
  TSIF(par == 0 && w == 1, 64);
  TSIF(par == 0 && w == 3 && !HALO_FIRST, 76);
#pragma unroll
  for (int j = 0; j < 10; j++) vlo[j] = movm(vlo[j]);
  const bool far0 = 2 * t > g, far1 = 2 * t + 1 > g;
  const uint32_t mfar = (far0 ? 0x0000FFFFu : 0u) | (far1 ? 0xFFFF0000u : 0u);
  float slo[4][2], shi[4][2], lg[2][2];
  uint32_t phi[4], plo[4], qml[4], qmh[4];
#pragma unroll
  for (int h = 0; h < 4; h++) {
    const int f = h == 0 ? 0 : h == 1 ? 3 : h == 2 ? 5 : 8, hf = h < 2 ? 2 : 7;
    const bool mine = (h & 1) ? t >= 2 : t < 2;
    qml[h] = mine ? qlo[hf] : 0u;
    qmh[h] = mine ? qhi[hf] : 0u;
    float a[4] = {0.f, 0.f, 0.f, 0.f}, c[4] = {0.f, 0.f, 0.f, 0.f};
    mma16816(a, qlo[f], qhi[f], qlo[f + 1], qhi[f + 1], klo[f], klo[f + 1]);
    mma16816(c, qlo[f], qhi[f], qlo[f + 1], qhi[f + 1], khi[f], khi[f + 1]);
    mma1688(a, qml[h], qmh[h], klo[hf]);
    mma1688(c, qml[h], qmh[h], khi[hf]);
    slo[h][0] = a[0];
    slo[h][1] = a[1];
    shi[h][0] = lg[h & 1][0] = far0 ? a[2] : c[2];
    shi[h][1] = lg[h & 1][1] = far1 ? a[3] : c[3];
    if (!ATT_MERGE && (h & 1)) softmax_two(lg, phi[h - 1], phi[h]);
  }
  TSIF(par == 0 && w == 1, 65);
  if (ATT_GATE == 3 && lane == 0) mbar_arrive(sb + OFF_BAR + 8 * B_ATT2 + (phi[3] & zero));
  wg_sync(1 + par);
  TSIF(par == 0 && w == 1, 66);
  const bool nohist = (w == 0) && (b < 8);
  const uint4* hp = g_halo + ((b - 8) * 2 + par) * 224 + lane;
  uint32_t tg[7];
  if (w > 0) {
    const uint4 v0 = lds128(xa + (w - 1) * 2560), v1 = lds128(xa + (w - 1) * 2560 + 512), v2 = lds128(xa + (w - 1) * 2560 + 1024);
    const uint4 v3 = lds128(xa + (w - 1) * 2560 + 1536), v4 = lds128(xa + (w - 1) * 2560 + 2048);
    kpv[0] = v0.x; kpv[1] = v0.y; kpv[2] = v0.z; kpv[3] = v0.w; kpv[4] = v1.x; kpv[5] = v1.y; kpv[6] = v1.z; kpv[7] = v1.w;
    kpv[8] = v2.x; kpv[9] = v2.y; vpv[0] = v2.z; vpv[1] = v2.w; vpv[2] = v3.x; vpv[3] = v3.y; vpv[4] = v3.z; vpv[5] = v3.w;
    vpv[6] = v4.x; vpv[7] = v4.y; vpv[8] = v4.z; vpv[9] = v4.w;
  } else if (nohist) {
#pragma unroll
    for (int j = 0; j < 10; j++) kpv[j] = vpv[j] = 0u;
  } else {
    TSIF(par == 0, 77);
    halo_read(kpv, vpv, tg, hp);
  }
  if (w == 0 && !nohist) {
    int spins = 0;
    while (true) {
      bool ok = true;
#pragma unroll
      for (int j = 0; j < 7; j++) ok = ok && tg[j] == tag;
      if (__all_sync(0xffffffffu, ok) || ++spins > SPIN_LIMIT) break;
      halo_read(kpv, vpv, tg, hp);
    }
    TSIF(par == 0, 79);
  }
#pragma unroll
  for (int h = 0; h < 4; h++) {
    const int f = h == 0 ? 0 : h == 1 ? 3 : h == 2 ? 5 : 8, hf = h < 2 ? 2 : 7;
    float a[4] = {0.f, 0.f, 0.f, 0.f};
    mma16816(a, qlo[f], qhi[f], qlo[f + 1], qhi[f + 1], kpv[f], kpv[f + 1]);
    mma1688(a, qml[h], qmh[h], kpv[hf]);
    const float ninf = __int_as_float(0xff800000);
    lg[h & 1][0] = far0 ? (nohist ? ninf : a[0]) : slo[h][0];
    lg[h & 1][1] = far1 ? (nohist ? ninf : a[1]) : slo[h][1];
    if (h & 1) {
      softmax_two(lg, plo[h - 1], plo[h]);
      if (ATT_MERGE) {
        const float lh[2][2] = {{shi[h - 1][0], shi[h - 1][1]}, {shi[h][0], shi[h][1]}};
        softmax_two(lh, phi[h - 1], phi[h]);
      }
    }
  }
  TSIF(par == 0 && w <= 1, 67 + w);
  if (ATT_GATE == 2 && lane == 0) mbar_arrive(sb + OFF_BAR + 8 * B_ATT2 + (plo[3] & zero));
  uint32_t ov[20];
#pragma unroll
  for (int hp = 0; hp < 2; hp++) {
    const int hf = hp ? 7 : 2;
    float sh[4] = {0.f, 0.f, 0.f, 0.f}, i0 = 0.f, i1 = 0.f;
#pragma unroll
    for (int e = 0; e < 2; e++) {
      const int h = 2 * hp + e, f = h == 0 ? 0 : h == 1 ? 3 : h == 2 ? 5 : 8;
      const uint32_t a0 = plo[h] & mfar, a2 = plo[h] & ~mfar, a3 = phi[h] & mfar, c1 = phi[h] & ~mfar;
      float sum[4] = {0.f, 0.f, 0.f, 0.f};
      mma1688(sum, plo[h], phi[h], 0x3F803F80u);
      const float r0 = rcp(sum[0]), r1 = rcp(sum[2]);
#pragma unroll
      for (int j = f; j < f + 2; j++) {
        float o[4] = {0.f, 0.f, 0.f, 0.f};
        mma16816(o, a0, 0u, a2, a3, vpv[j], vlo[j]);
        mma1688(o, 0u, c1, vhi[j]);
        ov[2 * j] = pack2(o[0] * r0, o[1] * r0);
        ov[2 * j + 1] = pack2(o[2] * r1, o[3] * r1);
      }
      const bool mine = e ? g >= 4 : g < 4;
      mma16816(sh, a0, 0u, a2, a3, mine ? vpv[hf] : 0u, mine ? vlo[hf] : 0u);
      mma1688(sh, 0u, c1, mine ? vhi[hf] : 0u);
      if (e == 0 || t >= 2) {
        i0 = r0;
        i1 = r1;
      }
    }
    ov[2 * hf] = pack2(sh[0] * i0, sh[1] * i0);
    ov[2 * hf + 1] = pack2(sh[2] * i1, sh[3] * i1);
  }
  if (ATT_GATE == 4 && lane == 0) mbar_arrive(sb + OFF_BAR + 8 * B_ATT2 + (ov[19] & zero));
  TS(32 + 4 * par + w);
  mbar_wait(sb + OFF_BAR + 8 * B_P1, 0);
  const uint32_t oa = sb + OFF_OA + (lane >> 4) * 2048 + (32 * w + 2 * (lane & 15) + par) * 16;
#pragma unroll
  for (int j = 0; j < 5; j++) stsm4(oa + 4096 * j, ov + 4 * j);
  TSIF(par == 0 && w == 0, 120);
  fence_async_smem();
  TSIF(par == 0 && w == 0, 121);
  __syncwarp();
  if (lane == 0) mbar_arrive(sb + OFF_BAR + 8 * B_ATTN);
  TSM(w == 0 || w == 2, 122 + par + (w == 2 ? 3 : 0));
}

struct Maps {
  CUtensorMap x, wm, wt, k, v, y, wo, qm, qt, om, ot, u;
};

__device__ __forceinline__ void load_stage(uint32_t sb, int kb, int b, const Maps& m) {
  const uint32_t st = sb + (kb & 3) * STAGE_BYTES, bar = sb + OFF_BAR + 8 * (B_FULL1 + (kb & 3));
  const int r = b >> 3, hg = b & 7, slab = kb - KV_KB;
  const bool kv = slab >= 0 && slab < 5;
  const uint32_t kbar = sb + OFF_BAR + 8 * (B_KV + slab), dst = sb + OFF_KVS + slab * KVS_BYTES;
  mbar_expect_tx(bar, STAGE_BYTES);
  if (kv) mbar_expect_tx(kbar, KVS_BYTES);
  tma_3d(st, &m.x, 64 * kb, 64 * r, 0, bar);
  if (kv && KV_MIX) tma_3d(dst, &m.k, 0, 32 * (b >> 1) - 3, 2 * slab + (b & 1), kbar);
  tma_3d(st + ST_W, &m.wm, 80 * hg + (tail_first(hg) ? 16 : 0), 64 * kb, 0, bar);
  if (kv && KV_MIX) tma_3d(dst + KVS_V, &m.v, 0, 32 * (b >> 1), 2 * slab + (b & 1), kbar);
  tma_3d(st + ST_WT, &m.wt, 80 * hg + (tail_first(hg) ? 0 : 64), 64 * kb, 0, bar);
  if (kv && !KV_MIX) tma_3d(dst, &m.k, 0, 32 * (b >> 1) - 3, 2 * slab + (b & 1), kbar);
  if (kv && !KV_MIX) tma_3d(dst + KVS_V, &m.v, 0, 32 * (b >> 1), 2 * slab + (b & 1), kbar);
}

__global__ void __launch_bounds__(NTHR, 1) fused_kernel(const __grid_constant__ Maps m, const Params p) {
  extern __shared__ __align__(1024) uint8_t smem[];
  const uint32_t sb = (uint32_t)__cvta_generic_to_shared(smem);
  const uint32_t bars = sb + OFF_BAR;
  const int tid = threadIdx.x, lane = tid & 31;
  int b = blockIdx.x;
  if (BMAP == 1) b = (((b & 63) >> 3) * 2 + (b & 1)) * 8 + (((b < 64 ? 0x6521 : 0x7430) >> (4 * ((b >> 1) & 3))) & 7);
  if (BMAP == 2) b = ((b & 63) >> 2) * 8 + (((b < 64 ? 0x6521 : 0x7430) >> (4 * (b & 3))) & 7);
  if (BMAP == 3) b = (((b & 63) >> 3) * 2 + (b & 1)) * 8 + (((b < 64 ? 0x7430 : 0x6521) >> (4 * ((b >> 1) & 3))) & 7);
  if (BMAP == 4) b = (((b >> 4) * 2 + (b & 1)) * 8) + ((b >> 1) & 7);
  if (BMAP == 5) b = 127 - b;
  const int r = b >> 3, hg = b & 7;

  if (tid == T_ISSUE) {
    TSM(true, 0);
#pragma unroll
    for (int i = 0; i < 4; i++) mbar_init(bars + 8 * (B_FULL1 + i), 1);
#pragma unroll
    for (int i = 0; i < 3; i++) mbar_init(bars + 8 * (B_KV + i), 1);
    fence_async_smem();
#pragma unroll 1
    for (int kb = 0; kb <= PRE2; kb++) load_stage(sb, kb, b, m);
  } else if (tid >= T_PF && tid < T_PF + 12) {
    tm_prefetch(&m.x + (tid - T_PF));
  } else if (tid == T_INIT) {
#pragma unroll
    for (int i = 0; i < 4; i++) mbar_init(bars + 8 * (B_EMPTY1 + i), 8);
#pragma unroll
    for (int i = 0; i < 8; i++) mbar_init(bars + 8 * (B_FULL2 + i), 1);
#pragma unroll
    for (int i = 0; i < 4; i++) mbar_init(bars + 8 * (B_EMPTY2 + i), 8);
#pragma unroll
    for (int i = 0; i < 4; i++) mbar_init(bars + 8 * (B_U + i), 1);
    mbar_init(bars + 8 * B_HA, 4);
    mbar_init(bars + 8 * B_GATE, 4);
    mbar_init(bars + 8 * B_HB, 1);
    mbar_init(bars + 8 * B_KVD, 4);
    mbar_init(bars + 8 * B_QF, 1);
    mbar_init(bars + 8 * B_ATTN, 8);
    mbar_init(bars + 8 * B_ATT2, 8);
    mbar_init(bars + 8 * B_P1, 8);
    mbar_init(bars + 8 * B_C34, 1);
    mbar_init(bars + 8 * B_YRB, 1);
#pragma unroll
    for (int i = 0; i < 5; i++) mbar_init(bars + 8 * (B_YST + i), 4);
#pragma unroll
    for (int i = 0; i < 5; i++) mbar_init(bars + 8 * (B_US + i), U_TMA ? 4 : 1);
    mbar_init(bars + 8 * B_YSIG, 1);
    mbar_init(bars + 8 * B_YFULL, 1);
    mbar_init(bars + 8 * B_EPOCH, 1);
    mbar_init(bars + 8 * B_PREP, 4);
    mbar_init(bars + 8 * B_USIG, 1);
    mbar_init(bars + 8 * B_WST, 1);
#pragma unroll
    for (int i = 3; i < 5; i++) mbar_init(bars + 8 * (B_KV + i), 1);
    mbar_init(bars + 8 * B_E3, 8);
    mbar_init(bars + 8 * B_LAST, 1);
    mbar_init(bars + 8 * B_OSIG, 1);
    mbar_init(bars + 8 * B_WOP, 1);
    fence_async_smem();
  }
  const int warp = __shfl_sync(0xffffffffu, tid >> 5, 0), wg = warp >> 2, w = warp & 3;
  __syncthreads();

  if (wg == 3) {
    asm volatile("setmaxnreg.dec.sync.aligned.u32 56;");
    if (w == 0) {
      if (lane == 0) {
#pragma unroll 1
        for (int kb = 1 + PRE2; kb < 10; kb++) {
          if (kb >= 4) mbar_wait(bars + 8 * (kb == 7 ? B_E3 : B_EMPTY1 + (kb & 3)), (kb >> 3) & 1);
          TSIF(kb >= 4, 44 + kb);
          load_stage(sb, kb, b, m);
          TSIF(kb == 3, 60);
          if (kb == TRIG_KB) mbar_arrive(bars + 8 * B_LAST);
        }
        mbar_wait(bars + 8 * B_WOP, 0);
        mbar_wait(bars + 8 * WL_TRIG, 0);
        mbar_wait(bars + 8 * B_EPOCH, 0);
        flag_wait(g_cnt + C_W + 32 * hg, (lds32(sb + OFF_EPOCH) + 1) * 16);
        TS(30);
#pragma unroll 1
        for (int j = 0; j < 8; j++) {
          if (j >= 6) mbar_wait(bars + 8 * (B_EMPTY2 + j - 6), 0);
          if (j == 4) mbar_wait(bars + 8 * B_ATTN, 0);
          TSIF(j >= 6, 100 + j);
          if (RF_GATE && j == 6) mbar_wait(bars + 8 * B_YSIG, 0);
          mbar_expect_tx(bars + 8 * (B_FULL2 + j), j == 0 ? WO_BYTES : j == 5 ? O_BYTES + WO_BYTES + 512 : O_BYTES + WO_BYTES);
          bulk_load(sb + off_w(j), g_WO + (hg * 8 + step_src(hg, j)) * 800, WO_BYTES, bars + 8 * (B_FULL2 + j));
        }
        mbar_wait(bars + 8 * (B_EMPTY2 + Q_SLOT), 0);
        mbar_expect_tx(bars + 8 * B_QF, O_BYTES);
        tma_2d(sb + OFF_QS, &m.qm, 80 * hg, 128 * r, bars + 8 * B_QF);
        if (!QBOX) tma_2d(sb + OFF_QT, &m.qt, 80 * hg + 64, 128 * r, bars + 8 * B_QF);
      }
    } else if (w == 1) {
      unsigned epoch = 0;
      if (lane == 0) {
        epoch = atomicAdd(g_cnt + C_LAUNCH, 1u) / NCTA;
        asm volatile("st.shared.u32 [%0], %1;" ::"r"(sb + OFF_EPOCH), "r"(epoch) : "memory");
        mbar_arrive(bars + 8 * B_EPOCH);
        mbar_wait(bars + 8 * B_KVD, 0);
        mbar_expect_tx(bars + 8 * B_HB, 5 * 4096);
#pragma unroll 1
        for (int c = 0; c < 5; c++) {
          if (c == 3) mbar_wait(bars + 8 * B_S3, 0);
          bulk_load(sb + off_ch(c) + U_BYTES, p.ssm_k + (5 * b + c) * SEQ, 4096, bars + 8 * B_HB);
        }
#pragma unroll
        for (int c = 0; c < 4; c++) mbar_expect_tx(bars + 8 * (B_U + c), c < 3 ? U_BYTES : 2 * U_BYTES);
        const uint4* usrc = g_U + 5 * b * U_PITCH;
        mbar_wait(bars + 8 * B_USIG, 0);
        flag_wait(g_cnt + C_PREP + 32 * (b & 15), (epoch + 1) * NCTA);
        TS(23);
#pragma unroll
        for (int c = 0; c < 5; c++) {
          if (c == 3 && U_TRIM) mbar_wait(bars + 8 * (B_U + 2), 0);
          bulk_load(sb + off_ch(c), usrc + c * U_PITCH, U_BYTES, bars + 8 * (B_U + (c < 3 ? c : 3)));
          TSIF(c == 0 || c == 4, 116 + (c >> 2));
        }
      }
      epoch = __shfl_sync(0xffffffffu, epoch, 0);
      if (lane < 8) {
        const int src = (b & ~7) | step_src(hg, lane);
        mbar_wait(bars + 8 * OP_TRIG, 0);
        TS(20);
        bool seen = false;
#pragma unroll 1
        for (int spins = 0; spins < SPIN_LIMIT; spins++) {
          const bool now = !seen && (int)(flag_read(g_cnt + C_O + 32 * src) - (epoch + 1)) >= 0;
          if (now && lane >= 1 && lane < 4) bulk_load(sb + off_o(lane), g_O + src * 1280, O_BYTES, bars + 8 * (B_FULL2 + lane));
          seen = seen || now;
          if (__all_sync(0xff, seen)) break;
        }
        TS(21);
        if (lane == 5) bulk_load(sb + OFF_GATE, g_gate + 128 * r, 512, bars + 8 * (B_FULL2 + 5));
#pragma unroll 1
        for (int j = 4; j < 8; j++) {
          if (lane == j) {
            mbar_wait(bars + 8 * (j < 6 ? B_C34 : B_EMPTY2 + j - 6), 0);
            if (RF_GATE && j == 6) mbar_wait(bars + 8 * B_YSIG, 0);
            bulk_load(sb + off_o(j), g_O + src * 1280, O_BYTES, bars + 8 * (B_FULL2 + j));
          }
          __syncwarp(0xff);
        }
        TS(22);
      }
    } else if (w == 2) {
      mbar_wait(bars + 8 * B_PREP, 0);
      flag_signal(g_cnt + C_PREP, 16, lane);
      TS(25);
      if (lane == 0) mbar_arrive(bars + 8 * B_USIG);
      mbar_wait(bars + 8 * B_GATE, 0);
      if (G_TMA) {
        if (lane == 0) {
          asm volatile("cp.async.bulk.global.shared::cta.bulk_group [%0], [%1], 64;\ncp.async.bulk.commit_group;\n"
                       "cp.async.bulk.wait_group.read 0;" ::"l"(g_gate + 16 * b), "r"(sb + OFF_GATE + 64 * hg) : "memory");
          bulk_load(sb + OFF_GATE + 64 * hg, g_gate + 16 * b, 64, bars + 8 * B_ORB);
        }
      } else if (((NOMB & 1) || O_RB) && lane == 0) {
        asm volatile("fence.release.gpu;" ::: "memory");
      }
      mbar_wait(bars + 8 * B_ATTN, 0);
      if (lane == 0) {
        if (O_DEFER) mbar_wait(bars + 8 * (B_U + 3), 0);
        asm volatile("cp.async.bulk.global.shared::cta.bulk_group [%0], [%1], 20480;\ncp.async.bulk.commit_group;"
                     ::"l"(g_O + b * 1280), "r"(sb + OFF_OA) : "memory");
        if (O_RB == 2) {
          asm volatile("cp.async.bulk.wait_group.read 0;" ::: "memory");
          mbar_expect_tx(bars + 8 * B_ORB, O_BYTES + 64 * G_TMA);
          bulk_load(sb + OFF_OA, g_O + b * 1280, O_BYTES, bars + 8 * B_ORB);
          mbar_wait(bars + 8 * B_ORB, 0);
          flag_bump(g_cnt + C_O + 32 * b);
        } else if (O_RB) asm volatile("cp.async.bulk.wait_group.read 0;" ::: "memory");
        else asm volatile("cp.async.bulk.wait_group 0;\nfence.proxy.async.global;" ::: "memory");
      }
      TS(74);
      if (O_RB == 2) {
      } else if (O_RB) {
        __syncwarp();
        unsigned v[5];
#pragma unroll
        for (int c = 0; c < 5; c++) v[c] = flag_read(reinterpret_cast<const unsigned*>(g_O + b * 1280 + 256 * c + 8 * lane + 7));
        const unsigned dep = __reduce_or_sync(0xffffffffu, (v[0] ^ v[1] ^ v[2] ^ v[3] ^ v[4]) & p.zero);
        if (lane == 0) flag_bump(g_cnt + C_O + 32 * b + dep);
      } else if (!(NOMB & 1)) flag_signal(g_cnt + C_O + 32 * b, 1, lane);
      else if (lane == 0) flag_bump(g_cnt + C_O + 32 * b);
      TS(26);
      if (lane == 0) mbar_arrive(bars + 8 * B_OSIG);

    } else {
      if (lane == 0) {
        uint4* dst = g_WO + (hg * 8 + (r >> 1)) * 800 + (r & 1) * 80;
        if (WPF) {
          mbar_wait(bars + 8 * WPF, 0);
          if (WPF_LIN)
            asm volatile("cp.async.bulk.prefetch.L2.global [%0], 6400;" ::"l"(p.wo + b * 3200) : "memory");
          else
            asm volatile("cp.async.bulk.prefetch.tensor.3d.L2.global [%0, {%1, %2, %3}];" ::"l"(&m.wo), "r"(0), "r"(40 * r), "r"(5 * hg) : "memory");
        }
        mbar_wait(bars + 8 * B_P1, 0);
        mbar_wait(bars + 8 * WB_TRIG, 0);
        mbar_expect_tx(bars + 8 * B_WST, WO_BYTES / 2);
        tma_3d(sb + OFF_WS, &m.wo, 0, 40 * r, 5 * hg, bars + 8 * B_WST);
        mbar_wait(bars + 8 * B_WST, 0);
        mbar_wait(bars + 8 * WO_TRIG, 0);
#pragma unroll 1
        for (int n = 0; n < 5; n++)
          asm volatile("cp.async.bulk.global.shared::cta.bulk_group [%0], [%1], 1280;" ::"l"(dst + 160 * n), "r"(sb + OFF_WS + 1280 * n) : "memory");
        if (W_RB) {
          asm volatile("cp.async.bulk.commit_group;\ncp.async.bulk.wait_group.read 0;" ::: "memory");
          mbar_expect_tx(bars + 8 * B_WST, WO_BYTES / 2);
#pragma unroll 1
          for (int n = 0; n < 5; n++) bulk_load(sb + OFF_WS + 1280 * n, dst + 160 * n, 1280, bars + 8 * B_WST);
          mbar_wait(bars + 8 * B_WST, 1);
        } else {
          asm volatile("cp.async.bulk.commit_group;\ncp.async.bulk.wait_group 0;\nfence.proxy.async.global;" ::: "memory");
          if (!(NOMB & 4)) asm volatile("fence.release.gpu;" ::: "memory");
        }
        flag_bump(g_cnt + C_W + 32 * hg);
        mbar_arrive(bars + 8 * B_WOP);
        TS(71);
        mbar_expect_tx(bars + 8 * B_C34, 3 * U_BYTES);
        mbar_expect_tx(bars + 8 * B_YRB, 2 * U_BYTES);
#pragma unroll 1
        for (int c = 0; c < 5; c++) {
          mbar_wait(bars + 8 * (B_YST + c), 0);
          asm volatile("cp.async.bulk.global.shared::cta.bulk_group [%0], [%1], 4096;\ncp.async.bulk.commit_group;\n"
                       "cp.async.bulk.wait_group.read 0;" ::"l"(g_Y + (5 * b + c) * Y_PITCH), "r"(sb + off_ch(c)) : "memory");
          bulk_load(sb + off_ch(c), g_Y + (5 * b + c) * Y_PITCH, U_BYTES, bars + 8 * (c < 3 ? B_C34 : B_YRB));
        }
        TS(75);
        mbar_wait(bars + 8 * B_C34, 0);
        mbar_wait(bars + 8 * B_YRB, 0);
        flag_bump(g_cnt + C_Y + 32 * (b >> 4));
        TS(27);
        mbar_arrive(bars + 8 * B_YSIG);
        mbar_expect_tx(bars + 8 * B_YFULL, 20480);
        flag_wait(g_cnt + C_Y + 32 * hg, (lds32(sb + OFF_EPOCH) + 1) * 16);
        TS(24);
        tma_2d(sb + OFF_YT, &m.y, 128 * r, 80 * hg, bars + 8 * B_YFULL);
        tma_2d(sb + OFF_YT + 10240, &m.y, 128 * r + 64, 80 * hg, bars + 8 * B_YFULL);
      }
    }
  } else {
    asm volatile("setmaxnreg.inc.sync.aligned.u32 152;");
    if (wg < 2) {
      float acc[120];
#pragma unroll
      for (int i = 0; i < 120; i++) acc[i] = 0.f;
      const uint32_t da = desc_lo(sb + wg * 8192, 16), db = desc_lo(sb + ST_W, 8192), dc = desc_lo(sb + ST_WT, 2048);
      if (PW1) pin<120>(acc);
      if (PW1 == 2) mbar_wait(bars + 8 * B_FULL1, 0);
#pragma unroll 1
      for (int kb = 0; kb < 10; kb++) {
        mbar_wait(bars + 8 * (B_FULL1 + (kb & 3)), (kb >> 2) & 1);
        const uint32_t so = (kb & 3) * (STAGE_BYTES >> 4);
        wg_fence();
#pragma unroll
        for (int k = 0; k < 4; k++) {
          WgSST<192>::mma<HI_SW128, HI_SW128>(acc, da + so + 2 * k, db + so + 128 * k, 1);
          WgSST<48>::mma<HI_SW128, HI_SW32>(acc + 96, da + so + 2 * k, dc + so + 32 * k, 1);
        }
        wg_commit();
        wg_wait<1>();
        if (kb > 0 && lane == 0) mbar_arrive(bars + 8 * (kb == 4 ? B_E3 : B_EMPTY1 + ((kb - 1) & 3)));
      }
      mbar_wait(bars + 8 * B_EPOCH, 0);
      const uint32_t tag = lds32(sb + OFF_EPOCH) + 1;
      mbar_wait(bars + 8 * B_S3, 0);
      wg_wait<0>();
      pin<120>(acc);
      if (lane == 0) mbar_arrive(bars + 8 * B_P1);
      TSM(w == 0, 3 + wg);
      attention(acc, sb, b, wg, w, lane, tag, p.zero);
    } else {
      const int tw = tid & 127, chl = 64 * (b & 1) + 8 * w + (lane >> 2);
      uint4* up = g_U + chl * U_PITCH + ((4 * (b >> 1) + (lane & 3)) ^ ((b >> 2) & 1));
      uint2 sw[10];
      uint32_t dv = 0;
      if (lane < 5) dv = __ldg(reinterpret_cast<const unsigned short*>(p.ssm_D) + 5 * b + lane);
#pragma unroll
      for (int i = 0; i < 10; i++) sw[i] = ldg64(reinterpret_cast<const uint2*>(p.shift_k) + chl + 128 * (i >> 1) + 32 * (i & 1));
      uint32_t tab[12];
      uint32_t tt[2];
      fft_tables(tab, tw);
      fft_twiddles(tt, tw);
      uint4 res[10];
#pragma unroll
      for (int i = 0; i < 10; i++) res[i] = make_uint4(0, 0, 0, 0);
#pragma unroll 1
      for (int slab = 0; slab < 5; slab++) {
#pragma unroll
        for (int i = 0; i < 8; i++) res[i] = res[i + 2];
        prep_slab(res + 8, sw, sb, slab, w, lane);
        TSIF(w == 0, 99 + 4 * slab);
#pragma unroll
        for (int i = 0; i < 8; i++) sw[i] = sw[i + 2];
      }
      TSIF(w == 0, 28);
      __syncwarp();
      if (lane == 0) mbar_arrive(bars + 8 * B_KVD + ((res[8].x ^ res[9].x) & p.zero));
      mbar_wait(bars + 8 * B_KVD, 0);
      fft_tables_store(tab, sb, tw);
      mbar_wait(bars + 8 * B_LAST, 0);
#pragma unroll
      for (int i = 0; i < 10; i++) up[(128 * (i >> 1) + 32 * (i & 1)) * U_PITCH] = res[i];
      __syncwarp();
      if (lane == 0) mbar_arrive(bars + 8 * B_PREP);
      TSIF(w == 0 && !U_TMA, 5);
      mbar_wait(bars + 8 * (G_AFTER ? B_USIG : B_LAST), 0);
      prep_gate(p, sb, b, w, lane);
      __syncwarp();
      if (lane == 0) mbar_arrive(bars + 8 * B_GATE);
      TSIF(w == 0, 72);
      mbar_wait(bars + 8 * B_HB, 0);
      TSIF(w == 0, 2);
      const uint32_t ha = sb + U_BYTES + ((tw >> 3) * 16 + 8 + (tw & 7)) * 16;
      uint4 hv[5];
#pragma unroll
      for (int c = 0; c < 5; c++) hv[c] = lds128(ha + off_ch(c));
      __syncwarp();
#pragma unroll
      for (int c = 0; c < 5; c++) sts128((ha ^ 16) + off_ch(c), hv[c].x, hv[c].y, hv[c].z, hv[c].w);
      asm volatile("st.shared.v2.u32 [%0], {%1, %2};" ::"r"(sb + OFF_TT + 8 * tw), "r"(tt[0]), "r"(tt[1]) : "memory");
      if (tw < 5) asm volatile("st.shared.f32 [%0], %1;" ::"r"(sb + OFF_D + 4 * tw), "f"(bf_lo(dv) * 0.125f) : "memory");
      fence_async_smem();
      __syncwarp();
      if (lane == 0) mbar_arrive(bars + 8 * B_HA);
      TSIF(w == 0, 6);
    }

    FftConst fc;
    TSM(w == 0 && wg == 0, 104);
    mbar_wait(bars + 8 * B_HA, 0);
    fft_matrices(fc, sb, w, lane);
    TSM(w == 0 && wg == 0, 105);
    TSM(w == 0 && wg == 2, 124);
#pragma unroll 1
    for (uint32_t tasks = wg == 0 ? TASK0 : wg == 1 ? TASK1 : TASK2; tasks; tasks >>= 4) {
      const int c = (tasks & 7) - 1;
      conv_channel(fc, sb, c, wg, w, lane);
      if (lane == 0) mbar_arrive(bars + 8 * (B_YST + c));
      TSM(w == 0, 10 + c);
    }

    if (wg < 2) {
      const int g = lane >> 2;
      float acc[40];
#pragma unroll
      for (int i = 0; i < 40; i++) acc[i] = 0.f;
      const uint32_t da = desc_lo(sb + wg * 1024, 2048), db = desc_lo(sb, 2560);
      if (!WO_FAST) mbar_wait(bars + 8 * (O_RB == 2 ? B_ORB : B_ATTN), 0);
      mbar_wait(bars + 8 * (B_YST + 3), 0);
      mbar_wait(bars + 8 * (B_YST + 4), 0);
      if (PW2 && !WO_FAST) mbar_wait(bars + 8 * B_FULL2, 0);
      TSM(w == 0, 15 + wg);
#pragma unroll 1
      for (int j = 0; j < 8; j++) {
        mbar_wait(bars + 8 * (B_FULL2 + j), 0);
        TSM(w == 0 && wg == 0, 44 + (j < 4 ? j : j + 6));
        const uint32_t oa = da + (off_o(j) >> 4), ob = db + (off_w(j) >> 4);
        wg_fence();
#pragma unroll
        for (int k = 0; k < 5; k++) WgSST<80>::mma<HI_NONE, HI_SW32>(acc, oa + 256 * k, ob + 32 * k, 1);
        wg_commit();
        wg_wait<1>();
        if (j >= 1 && j <= Q_SLOT + 1 && lane == 0) mbar_arrive(bars + 8 * (B_EMPTY2 + j - 1));
      }
      TSIF(w == 0 && wg == 0, 113);
      const int tr = 64 * wg + 16 * w + (lane & 15);
      const uint32_t fm = sb + OFF_QS + tr * 128, fx = (lane >> 4) ^ (tr & 7), fq = sb + OFF_QS + tr * 160 + (lane >> 4) * 16;
      const uint32_t ft = sb + OFF_QT + tr * 32 + (((lane >> 4) ^ (tr >> 2)) & 1) * 16;
      const float g0 = __uint_as_float(lds32(sb + OFF_GATE + (64 * wg + 16 * w + g) * 4));
      const float g1 = __uint_as_float(lds32(sb + OFF_GATE + (64 * wg + 16 * w + 8 + g) * 4));
      const uint32_t ga = pack2(g0, g0), gb = pack2(g1, g1);
      const uint32_t na = pack2(1.f - g0, 1.f - g0), nb = pack2(1.f - g1, 1.f - g1);

      uint32_t qf[20];
      mbar_wait(bars + 8 * B_QF, 0);
      TSM(w == 0 && wg == 0, 99);
#pragma unroll
      for (int j = 0; j < 5; j++) ldsm4(qf + 4 * j, QBOX ? fq + 32 * j : j < 4 ? fm + ((fx ^ (2 * j)) << 4) : ft);
      if (FUSE_MIX) {
#pragma unroll
        for (int i = 0; i < 20; i++) {
          qf[i] = bmul((i & 1) ? gb : ga, qf[i]);
          asm volatile("" : "+r"(qf[i]));
        }
      }
      wg_wait<0>();
      pin<40>(acc);
      TSM(w == 0, 17 + wg);
      uint32_t pb[20];
#pragma unroll
      for (int j = 0; j < 10; j++) {
        pb[2 * j] = bmul(na, pack2(acc[4 * j], acc[4 * j + 1]));
        pb[2 * j + 1] = bmul(nb, pack2(acc[4 * j + 2], acc[4 * j + 3]));
        asm volatile("" : "+r"(pb[2 * j]), "+r"(pb[2 * j + 1]));
      }
      const uint32_t ya = sb + OFF_YT + wg * 10240 + ((lane >> 4) * 8 + (lane & 7)) * 128 +
                          (((2 * w + (((lane >> 3) & 1) ^ wg)) ^ (lane & 7)) << 4);
      mbar_wait(bars + 8 * B_YFULL, 0);
      TSM(w == 0 && wg == 0, 19);
#pragma unroll
      for (int j = 0; j < 5; j++) {
        uint32_t y[4];
        ldsm4t(y, ya + 2048 * j);
#pragma unroll
        for (int i = 0; i < 4; i++)
          qf[4 * j + i] = FUSE_MIX ? bfma(qf[4 * j + i], y[i], pb[4 * j + i]) : badd(bmul((i & 1) ? gb : ga, bmul(qf[4 * j + i], y[i])), pb[4 * j + i]);
      }
#pragma unroll
      for (int j = 0; j < 5; j++) stsm4(QBOX ? fq + 32 * j : j < 4 ? fm + ((fx ^ (2 * j)) << 4) : ft, qf + 4 * j);
      fence_async_smem();
      __syncwarp();
      if (lane == 0) {
        const int row = 64 * wg + 16 * w;
        asm volatile("cp.async.bulk.tensor.2d.global.shared::cta.bulk_group [%0, {%2, %3}], [%1];"
                     ::"l"(&m.om), "r"(sb + OFF_QS + row * (QBOX ? 160 : 128)), "r"(80 * hg), "r"(128 * r + row) : "memory");
        if (!QBOX) asm volatile("cp.async.bulk.tensor.2d.global.shared::cta.bulk_group [%0, {%2, %3}], [%1];"
                     ::"l"(&m.ot), "r"(sb + OFF_QT + row * 32), "r"(80 * hg + 64), "r"(128 * r + row) : "memory");
        asm volatile("cp.async.bulk.commit_group;\ncp.async.bulk.wait_group.read 0;" ::: "memory");
      }
      TSM(w == 0 || w == 3, 40 + 2 * wg + (w & 1));
      if (ENDBAR) asm volatile("bar.sync 15, 256;" ::: "memory");
    }
  }
}

typedef CUresult (*EncodeFn)(CUtensorMap*, CUtensorMapDataType, cuuint32_t, void*, const cuuint64_t*, const cuuint64_t*,
                             const cuuint32_t*, const cuuint32_t*, CUtensorMapInterleave, CUtensorMapSwizzle,
                             CUtensorMapL2promotion, CUtensorMapFloatOOBfill);

void encode(EncodeFn fn, CUtensorMap* tm, const void* base, int rank, const cuuint64_t* dims, const cuuint64_t* strides,
            const cuuint32_t* box, CUtensorMapSwizzle swz) {
  const cuuint32_t ones[3] = {1, 1, 1};
  fn(tm, CU_TENSOR_MAP_DATA_TYPE_BFLOAT16, rank, const_cast<void*>(base), dims, strides, box, ones,
     CU_TENSOR_MAP_INTERLEAVE_NONE, swz, CU_TENSOR_MAP_L2_PROMOTION_L2_128B, CU_TENSOR_MAP_FLOAT_OOB_FILL_NONE);
}

}

extern "C" void kernel_launch(void* const* d_in, const int* in_sizes, int n_in, void* d_out, int out_size) {
  (void)in_sizes; (void)n_in; (void)out_size;
  Params p;
  p.q = (const __nv_bfloat16*)d_in[0];
  p.k = (const __nv_bfloat16*)d_in[1];
  p.v = (const __nv_bfloat16*)d_in[2];
  p.shift_k = (const __nv_bfloat16*)d_in[3];
  p.ssm_k = (const __nv_bfloat16*)d_in[4];
  p.ssm_D = (const __nv_bfloat16*)d_in[5];
  p.wqkv = (const __nv_bfloat16*)d_in[7];
  p.wo = (const __nv_bfloat16*)d_in[8];
  p.gate_w = (const __nv_bfloat16*)d_in[9];
  p.out = (__nv_bfloat16*)d_out;
  p.zero = 0;

  static EncodeFn fn = nullptr;
  static void *yaddr = nullptr, *uaddr = nullptr;
  if (!fn) {
    cudaDriverEntryPointQueryResult qr;
    void* f = nullptr;
    cudaGetDriverEntryPoint("cuTensorMapEncodeTiled", &f, cudaEnableDefault, &qr);
    fn = (EncodeFn)f;
    cudaGetSymbolAddress(&yaddr, g_Y);
    cudaGetSymbolAddress(&uaddr, g_U);
    cudaFuncSetAttribute(fused_kernel, cudaFuncAttributeMaxDynamicSharedMemorySize, SMEM_BYTES);
  }
  Maps m;
  {
    const cuuint64_t dims[3] = {640, 1024, 2}, st[2] = {2560, 1280};
    const cuuint32_t box[3] = {64, 64, 2};
    encode(fn, &m.x, p.q, 3, dims, st, box, CU_TENSOR_MAP_SWIZZLE_128B);
  }
  {
    const cuuint64_t dims[3] = {640, 640, 3}, st[2] = {3840, 1280};
    const cuuint32_t box[3] = {64, 64, 3}, boxt[3] = {16, 64, 3};
    encode(fn, &m.wm, p.wqkv, 3, dims, st, box, CU_TENSOR_MAP_SWIZZLE_128B);
    encode(fn, &m.wt, p.wqkv, 3, dims, st, boxt, CU_TENSOR_MAP_SWIZZLE_32B);
  }
  {
    const cuuint64_t dims[3] = {64, 2048, 10}, st[2] = {1280, 128};
    const cuuint32_t boxk[3] = {64, 35, 1}, boxv[3] = {64, 32, 1};
    encode(fn, &m.k, p.k, 3, dims, st, boxk, CU_TENSOR_MAP_SWIZZLE_128B);
    encode(fn, &m.v, p.v, 3, dims, st, boxv, CU_TENSOR_MAP_SWIZZLE_128B);
  }
  {
    const cuuint64_t dims[3] = {16, 640, 40}, st[2] = {1280, 32};
    const cuuint32_t box[3] = {16, 40, 5};
    encode(fn, &m.wo, p.wo, 3, dims, st, box, CU_TENSOR_MAP_SWIZZLE_32B);
  }
  {
    const cuuint64_t dims[2] = {2048, 640}, st[1] = {Y_PITCH * 16};
    const cuuint32_t box[2] = {64, 80};
    encode(fn, &m.y, yaddr, 2, dims, st, box, CU_TENSOR_MAP_SWIZZLE_128B);
    const cuuint64_t stu[1] = {U_PITCH * 16};
    const cuuint32_t boxu[2] = {32, 64};
    encode(fn, &m.u, uaddr, 2, dims, stu, boxu, CU_TENSOR_MAP_SWIZZLE_NONE);
  }
  {
    const cuuint64_t dims[2] = {640, 2048}, st[1] = {1280};
    const cuuint32_t bqm[2] = {QBOX ? 80 : 64, 128}, bqt[2] = {16, 128}, bom[2] = {QBOX ? 80 : 64, 16}, bot[2] = {16, 16};
    encode(fn, &m.qm, p.q, 2, dims, st, bqm, QBOX ? CU_TENSOR_MAP_SWIZZLE_NONE : CU_TENSOR_MAP_SWIZZLE_128B);
    encode(fn, &m.qt, p.q, 2, dims, st, bqt, CU_TENSOR_MAP_SWIZZLE_32B);
    encode(fn, &m.om, p.out, 2, dims, st, bom, QBOX ? CU_TENSOR_MAP_SWIZZLE_NONE : CU_TENSOR_MAP_SWIZZLE_128B);
    encode(fn, &m.ot, p.out, 2, dims, st, bot, CU_TENSOR_MAP_SWIZZLE_32B);
  }
  fused_kernel<<<NCTA, NTHR, SMEM_BYTES>>>(m, p);
}
```

```cpp
#include <cuda.h>
#include <cuda_bf16.h>
#include <cuda_runtime.h>
#include <stdint.h>

namespace {

constexpr int SEQ = 2048, DIM = 640, NCTA = 128, NTHR = 512;

#define TRIG_KB 9
#define KV_KB 2
#define DEV_EXIT 0
#define ATT_GATE 0
#define G_AFTER 0
#define FENCE_LO 0
#define FENCE_HI 0
#define PW1 2
#define PW2 1
#define ENDBAR 0
#define PAD_KB 0
#define Y_ALIAS 1
#define NOMB 0
#define SRC_ROT 0
#define WAIT_NS 0
#define WB_TRIG B_USIG
#define G_POS 0
#define TAILF 1
#define T_ISSUE 384
#define T_PF 416
#define T_INIT 448
#define ATT_MERGE 0
#define BMAP 1
#define PRE2 1
#define KV_MIX 0
#define O_DEFER 0
#define TASK0 0x52
#define TASK1 0x3
#define TASK2 0x41
#define HALO_FIRST 1
#define PREV_EARLY 0
#define Y_RB 2
#define O_RB 2
#define O_EAGER 1
#define OP_TRIG B_ATTN
#define FUSE_MIX 1
#define Q_EARLY 1
#define U_TRIM 1
#define Q_SLOT 3
#define G_TMA 1
#define W_RB 1
#define WPF B_S3
#define WPF_LIN 1
#define QBOX 0
#define ACQ 0
#define U_TMA 0
#define U_GATE 0
#define RF_GATE 0
#define WO_TRIG B_WST
#define WL_TRIG B_WOP
#define WO_GATE 4

constexpr uint32_t STAGE_BYTES = 47104, ST_W = 16384, ST_WT = 40960;
constexpr uint32_t O_BYTES = 20480, WO_BYTES = 12800;
constexpr uint32_t OFF_OA = 0;
constexpr uint32_t OFF_QS = Q_SLOT * O_BYTES, OFF_QT = OFF_QS + 16384;
constexpr uint32_t OFF_WC = 81920;
constexpr uint32_t OFF_WA = 94720;
constexpr uint32_t OFF_GATE = 145920;
constexpr uint32_t OFF_TT = 146432;
constexpr uint32_t OFF_KVX = 148480;
constexpr uint32_t OFF_CH3 = 163840;
constexpr uint32_t CH_BYTES = 12288, U_BYTES = 4096;
constexpr uint32_t OFF_FT = 225280, OFF_GT = 229376;
constexpr uint32_t OFF_CH0 = 188416;
constexpr uint32_t OFF_KVS = OFF_CH0, KVS_V = 4480, KVS_BYTES = 8576;
constexpr uint32_t OFF_WS = OFF_WA;
__device__ __forceinline__ uint32_t off_us(int s) { return OFF_CH0 + 4096 * ((0x65320 >> (4 * s)) & 7); }
constexpr uint32_t OFF_YT = 163840;
constexpr uint32_t OFF_BAR = 231936;
constexpr uint32_t SMEM_BYTES = OFF_BAR + 512;

enum : uint32_t {
  B_FULL1 = 0, B_EMPTY1 = 4, B_S3 = 7, B_FULL2 = 52, B_EMPTY2 = 13, B_U = 8, B_GATE = 12, B_HA = 19, B_HB = 20,
  B_ATTN = 21, B_C34 = 22, B_YRB = 23, B_YFULL = 24, B_EPOCH = 25, B_PREP = 26, B_P1 = 27, B_LAST = 28,
  B_E3 = 29, B_OSIG = 30, B_WOP = 31, B_USIG = 32, B_WST = 33, B_KV = 34, B_KVD = 39, B_QF = 17, B_ATT2 = 18, B_YST = 40,
  B_ORB = 45, B_CVD = 33 + 14, B_US = 45, B_YSIG = 50
};
constexpr uint32_t OFF_EPOCH = OFF_BAR + 8 * 51, OFF_D = OFF_BAR + 8 * 60;
__device__ __forceinline__ uint32_t off_o(int j) { return j < 4 ? OFF_OA + j * O_BYTES : j < 6 ? OFF_CH0 + (j - 4) * O_BYTES : OFF_OA + (j - 6) * O_BYTES; }
__device__ __forceinline__ uint32_t off_w(int j) { return j < 4 ? OFF_WA + j * WO_BYTES : j == 4 ? OFF_KVX : j == 5 ? OFF_WC : OFF_WA + (j - 6) * WO_BYTES; }
__device__ __forceinline__ int step_src(int hg, int j) {
  if (SRC_ROT == 2) {
    const int pos = (0x37621540 >> (4 * hg)) & 7;
    return j == 0 ? hg : (0x65217430 >> (4 * (j <= pos ? j - 1 : j))) & 7;
  }
  return SRC_ROT ? (hg + j) & 7 : j == 0 ? hg : j <= hg ? j - 1 : j;
}
__device__ __forceinline__ bool tail_first(int hg) { return TAILF && (hg & 3) == 3; }
__device__ __forceinline__ uint32_t off_ch(int c) { return (c < 3 ? OFF_CH0 : OFF_CH3 - 3 * CH_BYTES) + c * CH_BYTES; }

#define U_PITCH 264
__device__ __align__(1024) uint4 g_U[DIM * U_PITCH];
__device__ uint4 g_O[NCTA * 1280];
#define g_Y g_U
constexpr int Y_PITCH = U_PITCH;
__device__ uint4 g_WO[64 * 800];
__device__ uint4 g_halo[NCTA * 2 * 7 * 32];
__device__ __align__(128) float g_gate[SEQ + PAD_KB * 256];
__device__ unsigned g_cnt[32 * (1 + 2 * 16 + 8 + NCTA)];
constexpr int C_LAUNCH = 0, C_PREP = 32, C_Y = 32 * 17, C_W = 32 * 33, C_O = 32 * 41;

#define TSM(cond, slot) do { } while (0)
#define TSIF(cond, slot) do { if (__LINE__ >= FENCE_LO && __LINE__ < FENCE_HI) sched_fence(); } while (0)
__device__ __forceinline__ void sched_fence() {
  asm volatile("{\n.reg .pred p;\n.reg .u32 c;\nmov.u32 c, %%clock;\nsetp.eq.u32 p, c, 0;\n@p st.shared.u32 [%0], c;\n}"
               ::"r"(1024 + OFF_EPOCH + 4) : "memory");
}
#define TS(slot) TSIF(true, slot)

struct Params {
  const __nv_bfloat16 *q, *k, *v, *shift_k, *ssm_k, *ssm_D, *wqkv, *wo, *gate_w;
  __nv_bfloat16* out;
  uint32_t zero;
};

#define POLL_NS 0
constexpr int SPIN_LIMIT = 1 << 17;

__device__ __forceinline__ void mbar_init(uint32_t bar, uint32_t count) {
  asm volatile("mbarrier.init.shared::cta.b64 [%0], %1;" ::"r"(bar), "r"(count) : "memory");
}
__device__ __forceinline__ void mbar_expect_tx(uint32_t bar, uint32_t bytes) {
  asm volatile("mbarrier.arrive.expect_tx.shared::cta.b64 _, [%0], %1;" ::"r"(bar), "r"(bytes) : "memory");
}
__device__ __forceinline__ void mbar_arrive(uint32_t bar) {
  asm volatile("mbarrier.arrive.shared::cta.b64 _, [%0];" ::"r"(bar) : "memory");
}
__device__ __forceinline__ void mbar_wait(uint32_t bar, uint32_t parity) {
  uint32_t ok;
  int spins = 0;
  do {
    if (WAIT_NS)
      asm volatile("{\n.reg .pred p;\nmbarrier.try_wait.parity.shared::cta.b64 p, [%1], %2, %3;\nselp.b32 %0, 1, 0, p;\n}"
                   : "=r"(ok) : "r"(bar), "r"(parity), "r"(WAIT_NS) : "memory");
    else
      asm volatile("{\n.reg .pred p;\nmbarrier.try_wait.parity.shared::cta.b64 p, [%1], %2;\nselp.b32 %0, 1, 0, p;\n}"
                   : "=r"(ok) : "r"(bar), "r"(parity) : "memory");
    if (++spins > SPIN_LIMIT) break;
  } while (!ok);
}
__device__ __forceinline__ unsigned flag_read(const unsigned* p) {
  unsigned v;
  asm volatile("ld.relaxed.gpu.global.u32 %0, [%1];" : "=r"(v) : "l"(p) : "memory");
  return v;
}
__device__ __forceinline__ void flag_poll(const unsigned* p, unsigned target) {
  unsigned v;
  int spins = 0;
  do {
    if (POLL_NS && spins) __nanosleep(POLL_NS);
    asm volatile("ld.relaxed.gpu.global.u32 %0, [%1];" : "=r"(v) : "l"(p) : "memory");
    if (++spins > SPIN_LIMIT) break;
  } while ((int)(v - target) < 0);
}
__device__ __forceinline__ void flag_wait(const unsigned* p, unsigned target) {
  flag_poll(p, target);
  if (ACQ) asm volatile("fence.acquire.gpu;\nfence.proxy.async.global;" ::: "memory");
}
__device__ __forceinline__ void flag_signal(unsigned* p, int n, int lane) {
  if (lane == 0) asm volatile("fence.release.gpu;" ::: "memory");
  __syncwarp();
  if (lane < n) asm volatile("red.relaxed.gpu.global.add.u32 [%0], 1;" ::"l"(p + 32 * lane) : "memory");
}
__device__ __forceinline__ void flag_bump(unsigned* p) {
  asm volatile("red.relaxed.gpu.global.add.u32 [%0], 1;" ::"l"(p) : "memory");
}
__device__ __forceinline__ void fence_async_smem() { asm volatile("fence.proxy.async.shared::cta;" ::: "memory"); }
__device__ __forceinline__ void wg_sync(int id) { asm volatile("bar.sync %0, 128;" ::"r"(id) : "memory"); }

__device__ __forceinline__ void tma_2d(uint32_t dst, const CUtensorMap* tm, int c0, int c1, uint32_t bar) {
  asm volatile("cp.async.bulk.tensor.2d.shared::cluster.global.mbarrier::complete_tx::bytes [%0], [%1, {%3, %4}], [%2];"
               ::"r"(dst), "l"(tm), "r"(bar), "r"(c0), "r"(c1) : "memory");
}
__device__ __forceinline__ void tma_3d(uint32_t dst, const CUtensorMap* tm, int c0, int c1, int c2, uint32_t bar) {
  asm volatile("cp.async.bulk.tensor.3d.shared::cluster.global.mbarrier::complete_tx::bytes [%0], [%1, {%3, %4, %5}], [%2];"
               ::"r"(dst), "l"(tm), "r"(bar), "r"(c0), "r"(c1), "r"(c2) : "memory");
}
__device__ __forceinline__ void bulk_load(uint32_t dst, const void* src, uint32_t bytes, uint32_t bar) {
  asm volatile("cp.async.bulk.shared::cluster.global.mbarrier::complete_tx::bytes [%0], [%1], %2, [%3];"
               ::"r"(dst), "l"(src), "r"(bytes), "r"(bar) : "memory");
}
__device__ __forceinline__ void tm_prefetch(const CUtensorMap* tm) {
  asm volatile("prefetch.tensormap [%0];" ::"l"(tm) : "memory");
}

__device__ __forceinline__ void wg_fence() { asm volatile("wgmma.fence.sync.aligned;" ::: "memory"); }
__device__ __forceinline__ void wg_commit() { asm volatile("wgmma.commit_group.sync.aligned;" ::: "memory"); }
template <int N> __device__ __forceinline__ void wg_wait() { asm volatile("wgmma.wait_group.sync.aligned %0;" ::"n"(N) : "memory"); }
__device__ __forceinline__ uint32_t desc_lo(uint32_t addr, uint32_t lbo) { return ((addr & 0x3FFFF) >> 4) | ((lbo >> 4) << 16); }
constexpr uint32_t desc_hi(uint32_t sbo, uint32_t swz) { return (sbo >> 4) | (swz << 30); }
constexpr uint32_t HI_SW128 = desc_hi(1024, 1), HI_SW64 = desc_hi(512, 2), HI_SW32 = desc_hi(256, 3), HI_NONE = desc_hi(128, 0);
template <int N> __device__ __forceinline__ void pin(float* d) {
#pragma unroll
  for (int i = 0; i < N; i++) asm volatile("" : "+f"(d[i])::"memory");
}

__device__ __forceinline__ uint32_t lds32(uint32_t a) {
  uint32_t v;
  asm volatile("ld.volatile.shared.u32 %0, [%1];" : "=r"(v) : "r"(a) : "memory");
  return v;
}
__device__ __forceinline__ uint4 ldg128(const void* a) {
  uint4 v;
  asm volatile("ld.global.nc.v4.u32 {%0, %1, %2, %3}, [%4];" : "=r"(v.x), "=r"(v.y), "=r"(v.z), "=r"(v.w) : "l"(a) : "memory");
  return v;
}
__device__ __forceinline__ uint2 ldg64(const void* a) {
  uint2 v;
  asm volatile("ld.global.nc.v2.u32 {%0, %1}, [%2];" : "=r"(v.x), "=r"(v.y) : "l"(a) : "memory");
  return v;
}
__device__ __forceinline__ void ldsm4(uint32_t* r, uint32_t a) {
  asm volatile("ldmatrix.sync.aligned.m8n8.x4.shared.b16 {%0, %1, %2, %3}, [%4];"
               : "=r"(r[0]), "=r"(r[1]), "=r"(r[2]), "=r"(r[3]) : "r"(a) : "memory");
}
__device__ __forceinline__ void ldsm4t(uint32_t* r, uint32_t a) {
  asm volatile("ldmatrix.sync.aligned.m8n8.x4.trans.shared.b16 {%0, %1, %2, %3}, [%4];"
               : "=r"(r[0]), "=r"(r[1]), "=r"(r[2]), "=r"(r[3]) : "r"(a) : "memory");
}
__device__ __forceinline__ uint2 lds64(uint32_t a) {
  uint2 v;
  asm volatile("ld.shared.v2.u32 {%0, %1}, [%2];" : "=r"(v.x), "=r"(v.y) : "r"(a) : "memory");
  return v;
}
__device__ __forceinline__ uint4 lds128(uint32_t a) {
  uint4 v;
  asm volatile("ld.shared.v4.u32 {%0, %1, %2, %3}, [%4];" : "=r"(v.x), "=r"(v.y), "=r"(v.z), "=r"(v.w) : "r"(a) : "memory");
  return v;
}
__device__ __forceinline__ void sts128(uint32_t a, uint32_t x, uint32_t y, uint32_t z, uint32_t w) {
  asm volatile("st.shared.v4.u32 [%0], {%1, %2, %3, %4};" ::"r"(a), "r"(x), "r"(y), "r"(z), "r"(w) : "memory");
}
__device__ __forceinline__ void stsm4(uint32_t a, const uint32_t* r) {
  asm volatile("stmatrix.sync.aligned.m8n8.x4.shared.b16 [%0], {%1, %2, %3, %4};" ::"r"(a), "r"(r[0]), "r"(r[1]), "r"(r[2]), "r"(r[3]) : "memory");
}
__device__ __forceinline__ void stsm4t(uint32_t a, const uint32_t* r) {
  asm volatile("stmatrix.sync.aligned.m8n8.x4.trans.shared.b16 [%0], {%1, %2, %3, %4};" ::"r"(a), "r"(r[0]), "r"(r[1]), "r"(r[2]), "r"(r[3]) : "memory");
}
__device__ __forceinline__ uint32_t pack2(float lo, float hi) {
  uint32_t r;
  asm("cvt.rn.bf16x2.f32 %0, %1, %2;" : "=r"(r) : "f"(hi), "f"(lo));
  return r;
}
__device__ __forceinline__ uint32_t movm(uint32_t a) {
  uint32_t d;
  asm volatile("movmatrix.sync.aligned.m8n8.trans.b16 %0, %1;" : "=r"(d) : "r"(a));
  return d;
}
__device__ __forceinline__ uint32_t bmul(uint32_t a, uint32_t b) {
  uint32_t d;
  asm("mul.rn.bf16x2 %0, %1, %2;" : "=r"(d) : "r"(a), "r"(b));
  return d;
}
__device__ __forceinline__ uint32_t badd(uint32_t a, uint32_t b) {
  uint32_t d;
  asm("add.rn.bf16x2 %0, %1, %2;" : "=r"(d) : "r"(a), "r"(b));
  return d;
}
__device__ __forceinline__ uint32_t bfma(uint32_t a, uint32_t b, uint32_t c) {
  uint32_t d;
  asm("fma.rn.bf16x2 %0, %1, %2, %3;" : "=r"(d) : "r"(a), "r"(b), "r"(c));
  return d;
}
__device__ __forceinline__ float bf_lo(uint32_t x) { return __uint_as_float(x << 16); }
__device__ __forceinline__ float bf_hi(uint32_t x) { return __uint_as_float(x & 0xFFFF0000u); }
__device__ __forceinline__ float ex2(float x) {
  float y;
  asm("ex2.approx.ftz.f32 %0, %1;" : "=f"(y) : "f"(x));
  return y;
}
__device__ __forceinline__ float rcp(float x) {
  float y;
  asm("rcp.approx.ftz.f32 %0, %1;" : "=f"(y) : "f"(x));
  return y;
}
__device__ __forceinline__ void mma16816(float* d, uint32_t a0, uint32_t a1, uint32_t a2, uint32_t a3, uint32_t b0, uint32_t b1) {
  asm volatile("mma.sync.aligned.m16n8k16.row.col.f32.bf16.bf16.f32 {%0, %1, %2, %3}, {%4, %5, %6, %7}, {%8, %9}, {%0, %1, %2, %3};"
               : "+f"(d[0]), "+f"(d[1]), "+f"(d[2]), "+f"(d[3])
               : "r"(a0), "r"(a1), "r"(a2), "r"(a3), "r"(b0), "r"(b1));
}
__device__ __forceinline__ void mma1688(float* d, uint32_t a0, uint32_t a1, uint32_t b0) {
  asm volatile("mma.sync.aligned.m16n8k8.row.col.f32.bf16.bf16.f32 {%0, %1, %2, %3}, {%4, %5}, {%6}, {%0, %1, %2, %3};"
               : "+f"(d[0]), "+f"(d[1]), "+f"(d[2]), "+f"(d[3])
               : "r"(a0), "r"(a1), "r"(b0));
}

template <int N> struct WgRS;
template <int N> struct WgSST;
template <> struct WgRS<32> {
  template <uint32_t HB>
  static __device__ __forceinline__ void mma(float* d, const uint32_t* a, uint32_t db) {
    asm volatile("{\n.reg .pred p;\n.reg .b64 db;\nsetp.ne.b32 p, %22, 0;\n"
      "mov.b64 db, {%20, %21};\n"
      "wgmma.mma_async.sync.aligned.m64n32k16.f32.bf16.bf16 {"
      "%0, %1, %2, %3, %4, %5, %6, %7, %8, %9, %10, %11, %12, %13, %14, %15"
      "}, {%16, %17, %18, %19}, db, p, 1, 1, 1;\n}\n"
      : "+f"(d[0]), "+f"(d[1]), "+f"(d[2]), "+f"(d[3]), "+f"(d[4]), "+f"(d[5]), "+f"(d[6]), "+f"(d[7]),
        "+f"(d[8]), "+f"(d[9]), "+f"(d[10]), "+f"(d[11]), "+f"(d[12]), "+f"(d[13]), "+f"(d[14]), "+f"(d[15])
      : "r"(a[0]), "r"(a[1]), "r"(a[2]), "r"(a[3]), "r"(db), "n"(HB), "n"(1));
  }
  template <uint32_t HB>
  static __device__ __forceinline__ void set(float* d, const uint32_t* a, uint32_t db) {
    asm volatile("{\n.reg .pred p;\n.reg .b64 db;\nsetp.ne.b32 p, %22, 0;\n"
      "mov.b64 db, {%20, %21};\n"
      "wgmma.mma_async.sync.aligned.m64n32k16.f32.bf16.bf16 {"
      "%0, %1, %2, %3, %4, %5, %6, %7, %8, %9, %10, %11, %12, %13, %14, %15"
      "}, {%16, %17, %18, %19}, db, p, 1, 1, 1;\n}\n"
      : "=f"(d[0]), "=f"(d[1]), "=f"(d[2]), "=f"(d[3]), "=f"(d[4]), "=f"(d[5]), "=f"(d[6]), "=f"(d[7]),
        "=f"(d[8]), "=f"(d[9]), "=f"(d[10]), "=f"(d[11]), "=f"(d[12]), "=f"(d[13]), "=f"(d[14]), "=f"(d[15])
      : "r"(a[0]), "r"(a[1]), "r"(a[2]), "r"(a[3]), "r"(db), "n"(HB), "n"(0));
  }
};
template <> struct WgRS<64> {
  template <uint32_t HB>
  static __device__ __forceinline__ void mma(float* d, const uint32_t* a, uint32_t db) {
    asm volatile("{\n.reg .pred p;\n.reg .b64 db;\nsetp.ne.b32 p, %38, 0;\n"
      "mov.b64 db, {%36, %37};\n"
      "wgmma.mma_async.sync.aligned.m64n64k16.f32.bf16.bf16 {"
      "%0, %1, %2, %3, %4, %5, %6, %7, %8, %9, %10, %11, %12, %13, %14, %15, "
      "%16, %17, %18, %19, %20, %21, %22, %23, %24, %25, %26, %27, %28, %29, %30, %31"
      "}, {%32, %33, %34, %35}, db, p, 1, 1, 1;\n}\n"
      : "+f"(d[0]), "+f"(d[1]), "+f"(d[2]), "+f"(d[3]), "+f"(d[4]), "+f"(d[5]), "+f"(d[6]), "+f"(d[7]),
        "+f"(d[8]), "+f"(d[9]), "+f"(d[10]), "+f"(d[11]), "+f"(d[12]), "+f"(d[13]), "+f"(d[14]), "+f"(d[15]),
        "+f"(d[16]), "+f"(d[17]), "+f"(d[18]), "+f"(d[19]), "+f"(d[20]), "+f"(d[21]), "+f"(d[22]), "+f"(d[23]),
        "+f"(d[24]), "+f"(d[25]), "+f"(d[26]), "+f"(d[27]), "+f"(d[28]), "+f"(d[29]), "+f"(d[30]), "+f"(d[31])
      : "r"(a[0]), "r"(a[1]), "r"(a[2]), "r"(a[3]), "r"(db), "n"(HB), "n"(1));
  }
  template <uint32_t HB>
  static __device__ __forceinline__ void set(float* d, const uint32_t* a, uint32_t db) {
    asm volatile("{\n.reg .pred p;\n.reg .b64 db;\nsetp.ne.b32 p, %38, 0;\n"
      "mov.b64 db, {%36, %37};\n"
      "wgmma.mma_async.sync.aligned.m64n64k16.f32.bf16.bf16 {"
      "%0, %1, %2, %3, %4, %5, %6, %7, %8, %9, %10, %11, %12, %13, %14, %15, "
      "%16, %17, %18, %19, %20, %21, %22, %23, %24, %25, %26, %27, %28, %29, %30, %31"
      "}, {%32, %33, %34, %35}, db, p, 1, 1, 1;\n}\n"
      : "=f"(d[0]), "=f"(d[1]), "=f"(d[2]), "=f"(d[3]), "=f"(d[4]), "=f"(d[5]), "=f"(d[6]), "=f"(d[7]),
        "=f"(d[8]), "=f"(d[9]), "=f"(d[10]), "=f"(d[11]), "=f"(d[12]), "=f"(d[13]), "=f"(d[14]), "=f"(d[15]),
        "=f"(d[16]), "=f"(d[17]), "=f"(d[18]), "=f"(d[19]), "=f"(d[20]), "=f"(d[21]), "=f"(d[22]), "=f"(d[23]),
        "=f"(d[24]), "=f"(d[25]), "=f"(d[26]), "=f"(d[27]), "=f"(d[28]), "=f"(d[29]), "=f"(d[30]), "=f"(d[31])
      : "r"(a[0]), "r"(a[1]), "r"(a[2]), "r"(a[3]), "r"(db), "n"(HB), "n"(0));
  }
};
template <> struct WgSST<48> {
  template <uint32_t HA, uint32_t HB>
  static __device__ __forceinline__ void mma(float* d, uint32_t da, uint32_t db, int sc) {
    asm volatile("{\n.reg .pred p;\n.reg .b64 da, db;\nsetp.ne.b32 p, %28, 0;\n"
      "mov.b64 da, {%24, %25};\nmov.b64 db, {%26, %27};\n"
      "wgmma.mma_async.sync.aligned.m64n48k16.f32.bf16.bf16 {"
      "%0, %1, %2, %3, %4, %5, %6, %7, %8, %9, %10, %11, %12, %13, %14, %15, "
      "%16, %17, %18, %19, %20, %21, %22, %23"
      "}, da, db, p, 1, 1, 0, 1;\n}\n"
      : "+f"(d[0]), "+f"(d[1]), "+f"(d[2]), "+f"(d[3]), "+f"(d[4]), "+f"(d[5]), "+f"(d[6]), "+f"(d[7]),
        "+f"(d[8]), "+f"(d[9]), "+f"(d[10]), "+f"(d[11]), "+f"(d[12]), "+f"(d[13]), "+f"(d[14]), "+f"(d[15]),
        "+f"(d[16]), "+f"(d[17]), "+f"(d[18]), "+f"(d[19]), "+f"(d[20]), "+f"(d[21]), "+f"(d[22]), "+f"(d[23])
      : "r"(da), "n"(HA), "r"(db), "n"(HB), "r"(sc));
  }
};
template <> struct WgSST<80> {
  template <uint32_t HA, uint32_t HB>
  static __device__ __forceinline__ void mma(float* d, uint32_t da, uint32_t db, int sc) {
    asm volatile("{\n.reg .pred p;\n.reg .b64 da, db;\nsetp.ne.b32 p, %44, 0;\n"
      "mov.b64 da, {%40, %41};\nmov.b64 db, {%42, %43};\n"
      "wgmma.mma_async.sync.aligned.m64n80k16.f32.bf16.bf16 {"
      "%0, %1, %2, %3, %4, %5, %6, %7, %8, %9, %10, %11, %12, %13, %14, %15, "
      "%16, %17, %18, %19, %20, %21, %22, %23, %24, %25, %26, %27, %28, %29, %30, %31, "
      "%32, %33, %34, %35, %36, %37, %38, %39"
      "}, da, db, p, 1, 1, 0, 1;\n}\n"
      : "+f"(d[0]), "+f"(d[1]), "+f"(d[2]), "+f"(d[3]), "+f"(d[4]), "+f"(d[5]), "+f"(d[6]), "+f"(d[7]),
        "+f"(d[8]), "+f"(d[9]), "+f"(d[10]), "+f"(d[11]), "+f"(d[12]), "+f"(d[13]), "+f"(d[14]), "+f"(d[15]),
        "+f"(d[16]), "+f"(d[17]), "+f"(d[18]), "+f"(d[19]), "+f"(d[20]), "+f"(d[21]), "+f"(d[22]), "+f"(d[23]),
        "+f"(d[24]), "+f"(d[25]), "+f"(d[26]), "+f"(d[27]), "+f"(d[28]), "+f"(d[29]), "+f"(d[30]), "+f"(d[31]),
        "+f"(d[32]), "+f"(d[33]), "+f"(d[34]), "+f"(d[35]), "+f"(d[36]), "+f"(d[37]), "+f"(d[38]), "+f"(d[39])
      : "r"(da), "n"(HA), "r"(db), "n"(HB), "r"(sc));
  }
};
template <> struct WgSST<192> {
  template <uint32_t HA, uint32_t HB>
  static __device__ __forceinline__ void mma(float* d, uint32_t da, uint32_t db, int sc) {
    asm volatile("{\n.reg .pred p;\n.reg .b64 da, db;\nsetp.ne.b32 p, %100, 0;\n"
      "mov.b64 da, {%96, %97};\nmov.b64 db, {%98, %99};\n"
      "wgmma.mma_async.sync.aligned.m64n192k16.f32.bf16.bf16 {"
      "%0, %1, %2, %3, %4, %5, %6, %7, %8, %9, %10, %11, %12, %13, %14, %15, "
      "%16, %17, %18, %19, %20, %21, %22, %23, %24, %25, %26, %27, %28, %29, %30, %31, "
      "%32, %33, %34, %35, %36, %37, %38, %39, %40, %41, %42, %43, %44, %45, %46, %47, "
      "%48, %49, %50, %51, %52, %53, %54, %55, %56, %57, %58, %59, %60, %61, %62, %63, "
      "%64, %65, %66, %67, %68, %69, %70, %71, %72, %73, %74, %75, %76, %77, %78, %79, "
      "%80, %81, %82, %83, %84, %85, %86, %87, %88, %89, %90, %91, %92, %93, %94, %95"
      "}, da, db, p, 1, 1, 0, 1;\n}\n"
      : "+f"(d[0]), "+f"(d[1]), "+f"(d[2]), "+f"(d[3]), "+f"(d[4]), "+f"(d[5]), "+f"(d[6]), "+f"(d[7]),
        "+f"(d[8]), "+f"(d[9]), "+f"(d[10]), "+f"(d[11]), "+f"(d[12]), "+f"(d[13]), "+f"(d[14]), "+f"(d[15]),
        "+f"(d[16]), "+f"(d[17]), "+f"(d[18]), "+f"(d[19]), "+f"(d[20]), "+f"(d[21]), "+f"(d[22]), "+f"(d[23]),
        "+f"(d[24]), "+f"(d[25]), "+f"(d[26]), "+f"(d[27]), "+f"(d[28]), "+f"(d[29]), "+f"(d[30]), "+f"(d[31]),
        "+f"(d[32]), "+f"(d[33]), "+f"(d[34]), "+f"(d[35]), "+f"(d[36]), "+f"(d[37]), "+f"(d[38]), "+f"(d[39]),
        "+f"(d[40]), "+f"(d[41]), "+f"(d[42]), "+f"(d[43]), "+f"(d[44]), "+f"(d[45]), "+f"(d[46]), "+f"(d[47]),
        "+f"(d[48]), "+f"(d[49]), "+f"(d[50]), "+f"(d[51]), "+f"(d[52]), "+f"(d[53]), "+f"(d[54]), "+f"(d[55]),
        "+f"(d[56]), "+f"(d[57]), "+f"(d[58]), "+f"(d[59]), "+f"(d[60]), "+f"(d[61]), "+f"(d[62]), "+f"(d[63]),
        "+f"(d[64]), "+f"(d[65]), "+f"(d[66]), "+f"(d[67]), "+f"(d[68]), "+f"(d[69]), "+f"(d[70]), "+f"(d[71]),
        "+f"(d[72]), "+f"(d[73]), "+f"(d[74]), "+f"(d[75]), "+f"(d[76]), "+f"(d[77]), "+f"(d[78]), "+f"(d[79]),
        "+f"(d[80]), "+f"(d[81]), "+f"(d[82]), "+f"(d[83]), "+f"(d[84]), "+f"(d[85]), "+f"(d[86]), "+f"(d[87]),
        "+f"(d[88]), "+f"(d[89]), "+f"(d[90]), "+f"(d[91]), "+f"(d[92]), "+f"(d[93]), "+f"(d[94]), "+f"(d[95])
      : "r"(da), "n"(HA), "r"(db), "n"(HB), "r"(sc));
  }
};

struct FftConst {
  uint32_t f[2][4], fi[4][4];
  uint32_t ta[2][2], tb[2][2];
};
__device__ __forceinline__ void cis(int m, float scale, float& c, float& s) {
  const float a = (float)m * (-6.283185307179586f * scale);
  c = __cosf(a);
  s = __sinf(a);
}
__device__ __forceinline__ void fft_tables(uint32_t (&v)[12], int tw) {
  const int row = tw >> 2, ch = tw & 3;
#pragma unroll
  for (int i = 0; i < 4; i++) {
    float c[2], s[2], x[2];
#pragma unroll
    for (int e = 0; e < 2; e++) {
      cis((((32 * (8 * ch + 2 * i + e) + 15) * (4 * row - 63) + 2048) & 4095) - 2048, 1.f / 4096, c[e], s[e]);
      float gc, gs;
      cis((((row & 15) * (8 * (ch & 1) + 2 * i + e) + 8) & 15) - 8, 1.f / 16, gc, gs);
      x[e] = (row >> 4) == (ch >> 1) ? gc : (ch >> 1) ? gs : -gs;
    }
    v[i] = pack2(c[0] * 0.125f, c[1] * 0.125f);
    v[4 + i] = pack2(s[0] * 0.125f, s[1] * 0.125f);
    v[8 + i] = pack2(x[0], x[1]);
  }
#pragma unroll
  for (int i = 0; i < 12; i++) asm volatile("" : "+r"(v[i]));
}
__device__ __forceinline__ void fft_tables_store(const uint32_t (&v)[12], uint32_t sb, int tw) {
  const int row = tw >> 2;
  const uint32_t x = ((tw ^ (row >> 1)) & 3) << 4, a = sb + OFF_FT + (16 * (row >> 3) + (row & 7)) * 64 + x;
  sts128(a, v[0], v[1], v[2], v[3]);
  sts128(a + 512, v[4], v[5], v[6], v[7]);
  sts128(sb + OFF_GT + row * 64 + x, v[8], v[9], v[10], v[11]);
}
__device__ __forceinline__ void fft_twiddles(uint32_t (&v)[2], int tw) {
  float a[2], s[2];
#pragma unroll
  for (int i = 0; i < 2; i++) {
    float c;
    cis((2 * (2 * (tw & 3) + i) - 15) * (4 * (tw >> 2) - 63), 1.f / 4096, c, s[i]);
    a[i] = __fdividef(-s[i], 1.f + c);
  }
  v[0] = pack2(a[0], a[1]);
  v[1] = pack2(s[0], s[1]);
  asm volatile("" : "+r"(v[0]), "+r"(v[1]));
}
__device__ __forceinline__ void fft_matrices(FftConst& k, uint32_t sb, int w, int lane) {
  const uint32_t x = (lane >> 1) & 3;
  const uint2 t0 = lds64(sb + OFF_TT + 256 * w + 8 * lane), t1 = lds64(sb + OFF_TT + 256 * w + 8 * (lane ^ 3));
  k.ta[0][0] = t0.x;
  k.tb[0][0] = t0.y;
  k.ta[1][1] = __byte_perm(t1.x, 0, 0x1032);
  k.tb[1][1] = __byte_perm(t1.y, 0, 0x1032);
#pragma unroll
  for (int j = 0; j < 2; j++) {
    k.ta[1 - j][j] = k.ta[j][j] ^ 0x80008000u;
    k.tb[1 - j][j] = k.tb[j][j] ^ 0x80008000u;
    asm volatile("" : "+r"(k.ta[0][j]), "+r"(k.tb[0][j]), "+r"(k.ta[1][j]), "+r"(k.tb[1][j]));
  }
#pragma unroll
  for (int i = 0; i < 2; i++) {
    ldsm4(k.f[i], sb + OFF_FT + (16 * w + (lane & 15)) * 64 + (((2 * i + (lane >> 4)) ^ x) << 4));
    ldsm4t(k.fi[i], sb + OFF_FT + (32 * i + lane) * 64 + ((w ^ x) << 4));
#pragma unroll
    for (int j = 0; j < 4; j++) {
      k.fi[2 + i][j] = (j & 1) ? k.fi[i][j - 1] ^ 0x80008000u : k.fi[i][j + 1];
      asm volatile("" : "+r"(k.fi[2 + i][j]));
    }
  }
}
__device__ __forceinline__ void rot(uint32_t& x, uint32_t& y, uint32_t a, uint32_t b) {
  x = bfma(a, y, x);
  y = bfma(b, x, y);
  x = bfma(a, y, x);
}
__device__ __forceinline__ void twiddle_fwd(uint32_t (&a)[4][4], float* d, const FftConst& k) {
#pragma unroll
  for (int q = 0; q < 4; q++)
#pragma unroll
    for (int j = 0; j < 2; j++) {
      const float* x = d + 8 * q + 4 * j;
      uint32_t re = pack2(x[0], x[1]), im = pack2(x[2], x[3]);
      rot(re, im, k.ta[0][j], k.tb[0][j]);
      a[q & 2][2 * j + (q & 1)] = re;
      a[(q & 2) + 1][2 * j + (q & 1)] = im;
    }
}
__device__ __forceinline__ void g_step(float* d, const uint32_t (&a)[4][4], uint32_t dre, uint32_t dim) {
  WgRS<32>::set<HI_SW64>(d, a[0], dre);
  WgRS<32>::set<HI_SW64>(d + 16, a[2], dre);
  WgRS<32>::mma<HI_SW64>(d, a[1], dim);
  WgRS<32>::mma<HI_SW64>(d + 16, a[3], dim);
  wg_commit();
}

__device__ __forceinline__ void conv_channel(const FftConst& k, uint32_t sb, int c, int wg, int w, int lane) {
  const uint32_t cb = sb + off_ch(c), bars = sb + OFF_BAR;
  const uint32_t du = desc_lo(cb, 1024), dg = desc_lo(sb + OFF_GT, 16), dz = desc_lo(cb + U_BYTES, 16);
  float U[32], H[32];
  uint32_t a[4][4], e[4][4];
  const float dv = __uint_as_float(lds32(sb + OFF_D + 4 * c));
  wg_fence();
  WgRS<64>::set<HI_SW32>(H, k.f[0], du + 256);
  WgRS<64>::mma<HI_SW32>(H, k.f[1], du + 256 + 32);
  wg_commit();
  wg_wait<0>();
  pin<32>(H);
  twiddle_fwd(a, H, k);
  if (ATT_GATE) mbar_wait(bars + 8 * (ATT_GATE == 1 ? B_ATTN : B_ATT2), 0);
  mbar_wait(bars + 8 * (B_U + (c < 3 ? c : 3)), 0);
  TSM(w == 0 && c < 3, 7 + wg);
  wg_fence();
  WgRS<64>::set<HI_SW32>(U, k.f[0], du);
  WgRS<64>::mma<HI_SW32>(U, k.f[1], du + 32);
  wg_commit();
  g_step(H, a, dg, dg + 64);
  wg_wait<1>();
  pin<32>(U);
  twiddle_fwd(e, U, k);
  wg_fence();
  g_step(U, e, dg, dg + 64);
  wg_wait<0>();
  pin<32>(U);
  pin<32>(H);
#pragma unroll
  for (int j = 0; j < 2; j++) {
    float pr[4][2], pi[4][2];
#pragma unroll
    for (int x = 0; x < 2; x++) {
      H[4 * j + x] += dv;
#pragma unroll
      for (int m = 0; m < 4; m++) {
#pragma unroll
        for (int q = 0; q <= m; q++) {
          const int ih = 16 * (q >> 1) + 2 * (q & 1) + 4 * j + x, iu = 16 * ((m - q) >> 1) + 2 * ((m - q) & 1) + 4 * j + x;
          pr[m][x] = q ? fmaf(H[ih], U[iu], pr[m][x]) : H[ih] * U[iu];
          pi[m][x] = q ? fmaf(H[ih], U[iu + 8], pi[m][x]) : H[ih] * U[iu + 8];
          pr[m][x] = fmaf(-H[ih + 8], U[iu + 8], pr[m][x]);
          pi[m][x] = fmaf(H[ih + 8], U[iu], pi[m][x]);
        }
      }
    }
#pragma unroll
    for (int m = 0; m < 4; m++) {
      a[m & 2][2 * j + (m & 1)] = pack2(pr[m][0], pr[m][1]);
      a[(m & 2) + 1][2 * j + (m & 1)] = pack2(pi[m][0], pi[m][1]);
    }
  }
  wg_fence();
  g_step(U, a, dg + 64, dg);
  const uint32_t za = cb + U_BYTES + (8 * w + (lane & 7)) * 128 + (((lane >> 3) ^ (lane & 7)) << 4);
  const uint32_t ya = cb + (lane >> 4) * 1024 + (8 * w + (lane & 7)) * 32 + ((((lane >> 3) ^ (lane >> 2)) & 1) << 4);
  if (WO_GATE == 5 && lane == 0) mbar_arrive(bars + 8 * B_CVD);
  wg_sync(1 + wg);
  wg_wait<0>();
  pin<32>(U);
  TSIF(w == 0, 80 + c);
#pragma unroll
  for (int p = 0; p < 2; p++) {
#pragma unroll
    for (int i = 0; i < 4; i++) {
      const int j = i & 1;
      const float* x = U + 16 * p + 4 * j + (i & 2);
      e[p][i] = pack2(x[8], x[9]);
      e[2 + p][i] = pack2(x[0], x[1]);
      rot(e[p][i], e[2 + p][i], k.ta[1][j], k.tb[1][j]);
    }
    stsm4(za ^ (64 * p), e[p]);
    stsm4((za ^ (64 * p)) + 4096, e[2 + p]);
  }
  fence_async_smem();
  wg_sync(1 + wg);
  wg_fence();
  WgRS<64>::set<HI_SW128>(H, k.fi[0], dz);
#pragma unroll
  for (int ks = 1; ks < 4; ks++) WgRS<64>::mma<HI_SW128>(H, k.fi[ks], dz + 128 * ks);
  wg_commit();
  if (WO_GATE == 3 && lane == 0) mbar_arrive(bars + 8 * B_CVD);
  wg_wait<0>();
  pin<32>(H);
  if (WO_GATE == 4 && lane == 0) mbar_arrive(bars + 8 * B_CVD);
  TSIF(w == 0, 88 + c);
#pragma unroll
  for (int j = 0; j < 8; j++)
    a[j >> 2][j & 3] = j < 2 ? pack2(H[4 * j], H[4 * j + 1]) : pack2(H[4 * j] + H[4 * j - 6], H[4 * j + 1] + H[4 * j - 5]);
  stsm4(ya, a[0]);
  stsm4(ya + 2048, a[1]);
  fence_async_smem();
  __syncwarp();
}

__device__ __forceinline__ void prep_slab(uint4* res, const uint2* sw, uint32_t sb, int slab, int w, int lane) {
  const int t = lane & 3, tp = (lane & 7) >> 1, pos = 8 * tp + 2 * (((lane >> 3) + tp) & 3) + (lane & 1);
  const uint32_t base = sb + OFF_KVS + slab * KVS_BYTES + pos * 128;
  uint32_t kk[2][4][4], vv[2][4];
  mbar_wait(sb + OFF_BAR + 8 * (B_KV + slab), 0);
#pragma unroll
  for (int h = 0; h < 2; h++) {
#pragma unroll
    for (int j = 0; j < 4; j++) {
      const uint32_t a = base + 128 * j;
      ldsm4t(kk[h][j], a + (((w + 4 * h) ^ ((a >> 7) & 7)) << 4));
    }
    const uint32_t a = base + KVS_V;
    ldsm4t(vv[h], a + (((w + 4 * h) ^ ((a >> 7) & 7)) << 4));
  }
#pragma unroll
  for (int h = 0; h < 2; h++) {
    uint32_t (&k)[4][4] = kk[h];
    uint32_t (&v)[4] = vv[h];
    const uint32_t w0 = __byte_perm(sw[h].x, 0, 0x1010), w1 = __byte_perm(sw[h].x, 0, 0x3232);
    const uint32_t w2 = __byte_perm(sw[h].y, 0, 0x1010), w3 = __byte_perm(sw[h].y, 0, 0x3232);
#pragma unroll
    for (int m = 0; m < 4; m++)
      v[m] = bmul(badd(badd(badd(bmul(k[0][m], w3), bmul(k[1][m], w2)), bmul(k[2][m], w1)), bmul(k[3][m], w0)), v[m]);
    uint32_t a[4];
#pragma unroll
    for (int m = 0; m < 4; m++) a[m] = (t & 1) ? v[(m + 3) & 3] : v[m];
    res[h] = (t & 2) ? make_uint4(a[2], a[3], a[0], a[1]) : make_uint4(a[0], a[1], a[2], a[3]);
  }
}

__device__ __forceinline__ void prep_gate(const Params& p, uint32_t sb, int b, int w, int lane) {
  uint2 gw[5], x[4][5];
#pragma unroll
  for (int j = 0; j < 5; j++) gw[j] = ldg64(reinterpret_cast<const uint2*>(p.gate_w) + lane + 32 * j);
#pragma unroll
  for (int i = 0; i < 4; i++)
#pragma unroll
    for (int j = 0; j < 5; j++)
      x[i][j] = ldg64(reinterpret_cast<const uint2*>(p.q) + (16 * b + 4 * w + i) * (DIM / 4) + lane + 32 * j);
  float s[4];
#pragma unroll
  for (int i = 0; i < 4; i++) {
    s[i] = 0.f;
#pragma unroll
    for (int j = 0; j < 5; j++) {
      const uint32_t m0 = bmul(x[i][j].x, gw[j].x), m1 = bmul(x[i][j].y, gw[j].y);
      s[i] += (bf_lo(m0) + bf_hi(m0)) + (bf_lo(m1) + bf_hi(m1));
    }
  }
  const bool h = lane & 16, q = lane & 8;
  const float a = (h ? s[2] : s[0]) + __shfl_xor_sync(0xffffffffu, h ? s[0] : s[2], 16);
  const float c = (h ? s[3] : s[1]) + __shfl_xor_sync(0xffffffffu, h ? s[1] : s[3], 16);
  float z = (q ? c : a) + __shfl_xor_sync(0xffffffffu, q ? a : c, 8);
#pragma unroll
  for (int o = 4; o > 0; o >>= 1) z += __shfl_xor_sync(0xffffffffu, z, o);
  z = bf_lo(pack2(z, 0.f));
  z = bf_lo(pack2(__fdividef(1.f, 1.f + __expf(-z)), 0.f));
  if (G_TMA) {
    mbar_wait(sb + OFF_BAR + 8 * B_S3, 0);
    if ((lane & 7) == 0) asm volatile("st.shared.f32 [%0], %1;" ::"r"(sb + OFF_GATE + 64 * (b & 7) + 16 * w + (lane >> 1)), "f"(z) : "memory");
    fence_async_smem();
  } else if ((lane & 7) == 0) {
    g_gate[16 * b + 4 * w + (lane >> 3)] = z;
  }
}

__device__ __forceinline__ uint32_t bmax(uint32_t a, uint32_t b) {
  uint32_t d;
  asm("max.bf16x2 %0, %1, %2;" : "=r"(d) : "r"(a), "r"(b));
  return d;
}
__device__ __forceinline__ void softmax_two(const float (&l)[2][2], uint32_t& p0, uint32_t& p1) {
  constexpr float kScale = 0.22360679774997896f, kLog2e = 1.4426950408889634f;
  const uint32_t r0 = pack2(l[0][0], l[1][0]), r1 = pack2(l[0][1], l[1][1]);
  const uint32_t x0 = pack2(bf_lo(r0) * kScale, bf_hi(r0) * kScale), x1 = pack2(bf_lo(r1) * kScale, bf_hi(r1) * kScale);
  uint32_t m = bmax(x0, x1);
  m = bmax(m, __shfl_xor_sync(0xffffffffu, m, 1));
  m = bmax(m, __shfl_xor_sync(0xffffffffu, m, 2));
  const float m0 = bf_lo(m) * kLog2e, m1 = bf_hi(m) * kLog2e;
  p0 = pack2(ex2(bf_lo(x0) * kLog2e - m0), ex2(bf_lo(x1) * kLog2e - m0));
  p1 = pack2(ex2(bf_hi(x0) * kLog2e - m1), ex2(bf_hi(x1) * kLog2e - m1));
}

__device__ __forceinline__ void halo_read(uint32_t (&kpv)[10], uint32_t (&vpv)[10], uint32_t (&tg)[7], const uint4* hp) {
#pragma unroll
  for (int j = 0; j < 7; j++) {
    uint32_t x0, x1, x2;
    asm volatile("ld.relaxed.gpu.global.v4.u32 {%0, %1, %2, %3}, [%4];"
                 : "=r"(x0), "=r"(x1), "=r"(x2), "=r"(tg[j]) : "l"(hp + 32 * j) : "memory");
    if (j < 4) kpv[3 * j] = x0; else vpv[3 * j - 10] = x0;
    if (j < 3) kpv[3 * j + 1] = x1; else vpv[3 * j - 9] = x1;
    if (j < 3) kpv[3 * j + 2] = x2; else if (j < 6) vpv[3 * j - 8] = x2;
  }
}

template <int ROT>
__device__ __forceinline__ void pack_qkv(const float* acc, uint32_t (&qlo)[10], uint32_t (&qhi)[10], uint32_t (&klo)[10],
                                         uint32_t (&khi)[10], uint32_t (&vlo)[10], uint32_t (&vhi)[10]) {
#pragma unroll
  for (int j = 0; j < 10; j++) {
    const int x = (j + ROT) % 10, tq = x < 8 ? x : 16 + x, tk = x < 8 ? 8 + x : 18 + x, tv = x < 8 ? 16 + x : 20 + x;
    khi[j] = pack2(acc[4 * tk + 2], acc[4 * tk + 3]);
    vhi[j] = movm(pack2(acc[4 * tv + 2], acc[4 * tv + 3]));
    qlo[j] = pack2(acc[4 * tq], acc[4 * tq + 1]);
    qhi[j] = pack2(acc[4 * tq + 2], acc[4 * tq + 3]);
    klo[j] = pack2(acc[4 * tk], acc[4 * tk + 1]);
    vlo[j] = pack2(acc[4 * tv], acc[4 * tv + 1]);
    asm volatile("" : "+r"(khi[j]), "+r"(qlo[j]), "+r"(qhi[j]), "+r"(klo[j]), "+r"(vlo[j]));
  }
}

template <int ROT> __device__ __forceinline__ void halo_send(const float* acc, uint4* ho, uint32_t tag) {
#pragma unroll
  for (int j = 0; j < 7; j++) {
    uint32_t x[3];
#pragma unroll
    for (int e = 0; e < 3; e++) {
      const int i = 3 * j + e, y = (i % 10 + ROT) % 10, tk = y < 8 ? 8 + y : 18 + y, tv = y < 8 ? 16 + y : 20 + y;
      x[e] = i < 10 ? pack2(acc[4 * tk + 2], acc[4 * tk + 3]) : i < 20 ? movm(pack2(acc[4 * tv + 2], acc[4 * tv + 3])) : 0u;
    }
    asm volatile("st.relaxed.gpu.global.v4.u32 [%0], {%1, %2, %3, %4};" ::"l"(ho + 32 * j), "r"(x[0]), "r"(x[1]), "r"(x[2]), "r"(tag) : "memory");
  }
}

__device__ __forceinline__ void attention(float* acc, uint32_t sb, int b, int par, int w, int lane, uint32_t tag, uint32_t zero) {
  const int g = lane >> 2, t = lane & 3;
  uint32_t klo[10], khi[10], vlo[10], vhi[10], qlo[10], qhi[10], kpv[10], vpv[10];
  if (HALO_FIRST && w == 3 && b < NCTA - 8) {
    uint4* ho = g_halo + (b * 2 + par) * 224 + lane;
    if (tail_first(b & 7)) halo_send<8>(acc, ho, tag);
    else halo_send<0>(acc, ho, tag);
    TSIF(par == 0, 76);
    pin<120>(acc);
  }
  if (tail_first(b & 7)) pack_qkv<8>(acc, qlo, qhi, klo, khi, vlo, vhi);
  else pack_qkv<0>(acc, qlo, qhi, klo, khi, vlo, vhi);
  const uint32_t xa = sb + OFF_KVX + (par * 3) * 2560 + lane * 16;
  if (w < 3) {
    sts128(xa + w * 2560, khi[0], khi[1], khi[2], khi[3]);
    sts128(xa + w * 2560 + 512, khi[4], khi[5], khi[6], khi[7]);
    sts128(xa + w * 2560 + 1024, khi[8], khi[9], vhi[0], vhi[1]);
    sts128(xa + w * 2560 + 1536, vhi[2], vhi[3], vhi[4], vhi[5]);
    sts128(xa + w * 2560 + 2048, vhi[6], vhi[7], vhi[8], vhi[9]);
  } else if (!HALO_FIRST && b < NCTA - 8) {
    uint4* ho = g_halo + (b * 2 + par) * 224 + lane;
#pragma unroll
    for (int j = 0; j < 7; j++) {
      const uint32_t x0 = j < 4 ? khi[3 * j] : vhi[3 * j - 10], x1 = j < 3 ? khi[3 * j + 1] : vhi[3 * j - 9];
      const uint32_t x2 = j < 3 ? khi[3 * j + 2] : j < 6 ? vhi[3 * j - 8] : 0u;
      asm volatile("st.relaxed.gpu.global.v4.u32 [%0], {%1, %2, %3, %4};" ::"l"(ho + 32 * j), "r"(x0), "r"(x1), "r"(x2), "r"(tag) : "memory");
    }
  }
  TSIF(par == 0 && w == 1, 64);
  TSIF(par == 0 && w == 3 && !HALO_FIRST, 76);
#pragma unroll
  for (int j = 0; j < 10; j++) vlo[j] = movm(vlo[j]);
  const bool far0 = 2 * t > g, far1 = 2 * t + 1 > g;
  const uint32_t mfar = (far0 ? 0x0000FFFFu : 0u) | (far1 ? 0xFFFF0000u : 0u);
  float slo[4][2], shi[4][2], lg[2][2];
  uint32_t phi[4], plo[4], qml[4], qmh[4];
#pragma unroll
  for (int h = 0; h < 4; h++) {
    const int f = h == 0 ? 0 : h == 1 ? 3 : h == 2 ? 5 : 8, hf = h < 2 ? 2 : 7;
    const bool mine = (h & 1) ? t >= 2 : t < 2;
    qml[h] = mine ? qlo[hf] : 0u;
    qmh[h] = mine ? qhi[hf] : 0u;
    float a[4] = {0.f, 0.f, 0.f, 0.f}, c[4] = {0.f, 0.f, 0.f, 0.f};
    mma16816(a, qlo[f], qhi[f], qlo[f + 1], qhi[f + 1], klo[f], klo[f + 1]);
    mma16816(c, qlo[f], qhi[f], qlo[f + 1], qhi[f + 1], khi[f], khi[f + 1]);
    mma1688(a, qml[h], qmh[h], klo[hf]);
    mma1688(c, qml[h], qmh[h], khi[hf]);
    slo[h][0] = a[0];
    slo[h][1] = a[1];
    shi[h][0] = lg[h & 1][0] = far0 ? a[2] : c[2];
    shi[h][1] = lg[h & 1][1] = far1 ? a[3] : c[3];
    if (!ATT_MERGE && (h & 1)) softmax_two(lg, phi[h - 1], phi[h]);
  }
  TSIF(par == 0 && w == 1, 65);
  if (ATT_GATE == 3 && lane == 0) mbar_arrive(sb + OFF_BAR + 8 * B_ATT2 + (phi[3] & zero));
  wg_sync(1 + par);
  TSIF(par == 0 && w == 1, 66);
  const bool nohist = (w == 0) && (b < 8);
  const uint4* hp = g_halo + ((b - 8) * 2 + par) * 224 + lane;
  uint32_t tg[7];
  if (w > 0) {
    const uint4 v0 = lds128(xa + (w - 1) * 2560), v1 = lds128(xa + (w - 1) * 2560 + 512), v2 = lds128(xa + (w - 1) * 2560 + 1024);
    const uint4 v3 = lds128(xa + (w - 1) * 2560 + 1536), v4 = lds128(xa + (w - 1) * 2560 + 2048);
    kpv[0] = v0.x; kpv[1] = v0.y; kpv[2] = v0.z; kpv[3] = v0.w; kpv[4] = v1.x; kpv[5] = v1.y; kpv[6] = v1.z; kpv[7] = v1.w;
    kpv[8] = v2.x; kpv[9] = v2.y; vpv[0] = v2.z; vpv[1] = v2.w; vpv[2] = v3.x; vpv[3] = v3.y; vpv[4] = v3.z; vpv[5] = v3.w;
    vpv[6] = v4.x; vpv[7] = v4.y; vpv[8] = v4.z; vpv[9] = v4.w;
  } else if (nohist) {
#pragma unroll
    for (int j = 0; j < 10; j++) kpv[j] = vpv[j] = 0u;
  } else {
    TSIF(par == 0, 77);
    halo_read(kpv, vpv, tg, hp);
  }
  if (w == 0 && !nohist) {
    int spins = 0;
    while (true) {
      bool ok = true;
#pragma unroll
      for (int j = 0; j < 7; j++) ok = ok && tg[j] == tag;
      if (__all_sync(0xffffffffu, ok) || ++spins > SPIN_LIMIT) break;
      halo_read(kpv, vpv, tg, hp);
    }
    TSIF(par == 0, 79);
  }
#pragma unroll
  for (int h = 0; h < 4; h++) {
    const int f = h == 0 ? 0 : h == 1 ? 3 : h == 2 ? 5 : 8, hf = h < 2 ? 2 : 7;
    float a[4] = {0.f, 0.f, 0.f, 0.f};
    mma16816(a, qlo[f], qhi[f], qlo[f + 1], qhi[f + 1], kpv[f], kpv[f + 1]);
    mma1688(a, qml[h], qmh[h], kpv[hf]);
    const float ninf = __int_as_float(0xff800000);
    lg[h & 1][0] = far0 ? (nohist ? ninf : a[0]) : slo[h][0];
    lg[h & 1][1] = far1 ? (nohist ? ninf : a[1]) : slo[h][1];
    if (h & 1) {
      softmax_two(lg, plo[h - 1], plo[h]);
      if (ATT_MERGE) {
        const float lh[2][2] = {{shi[h - 1][0], shi[h - 1][1]}, {shi[h][0], shi[h][1]}};
        softmax_two(lh, phi[h - 1], phi[h]);
      }
    }
  }
  TSIF(par == 0 && w <= 1, 67 + w);
  if (ATT_GATE == 2 && lane == 0) mbar_arrive(sb + OFF_BAR + 8 * B_ATT2 + (plo[3] & zero));
  uint32_t ov[20];
#pragma unroll
  for (int hp = 0; hp < 2; hp++) {
    const int hf = hp ? 7 : 2;
    float sh[4] = {0.f, 0.f, 0.f, 0.f}, i0 = 0.f, i1 = 0.f;
#pragma unroll
    for (int e = 0; e < 2; e++) {
      const int h = 2 * hp + e, f = h == 0 ? 0 : h == 1 ? 3 : h == 2 ? 5 : 8;
      const uint32_t a0 = plo[h] & mfar, a2 = plo[h] & ~mfar, a3 = phi[h] & mfar, c1 = phi[h] & ~mfar;
      float sum[4] = {0.f, 0.f, 0.f, 0.f};
      mma1688(sum, plo[h], phi[h], 0x3F803F80u);
      const float r0 = rcp(sum[0]), r1 = rcp(sum[2]);
#pragma unroll
      for (int j = f; j < f + 2; j++) {
        float o[4] = {0.f, 0.f, 0.f, 0.f};
        mma16816(o, a0, 0u, a2, a3, vpv[j], vlo[j]);
        mma1688(o, 0u, c1, vhi[j]);
        ov[2 * j] = pack2(o[0] * r0, o[1] * r0);
        ov[2 * j + 1] = pack2(o[2] * r1, o[3] * r1);
      }
      const bool mine = e ? g >= 4 : g < 4;
      mma16816(sh, a0, 0u, a2, a3, mine ? vpv[hf] : 0u, mine ? vlo[hf] : 0u);
      mma1688(sh, 0u, c1, mine ? vhi[hf] : 0u);
      if (e == 0 || t >= 2) {
        i0 = r0;
        i1 = r1;
      }
    }
    ov[2 * hf] = pack2(sh[0] * i0, sh[1] * i0);
    ov[2 * hf + 1] = pack2(sh[2] * i1, sh[3] * i1);
  }
  if (ATT_GATE == 4 && lane == 0) mbar_arrive(sb + OFF_BAR + 8 * B_ATT2 + (ov[19] & zero));
  TS(32 + 4 * par + w);
  mbar_wait(sb + OFF_BAR + 8 * B_P1, 0);
  const uint32_t oa = sb + OFF_OA + (lane >> 4) * 2048 + (32 * w + 2 * (lane & 15) + par) * 16;
#pragma unroll
  for (int j = 0; j < 5; j++) stsm4(oa + 4096 * j, ov + 4 * j);
  TSIF(par == 0 && w == 0, 120);
  fence_async_smem();
  TSIF(par == 0 && w == 0, 121);
  __syncwarp();
  if (lane == 0) mbar_arrive(sb + OFF_BAR + 8 * B_ATTN);
  TSM(w == 0 || w == 2, 122 + par + (w == 2 ? 3 : 0));
}

struct Maps {
  CUtensorMap x, wm, wt, k, v, y, wo, qm, qt, om, ot, u;
};

__device__ __forceinline__ void load_stage(uint32_t sb, int kb, int b, const Maps& m) {
  const uint32_t st = sb + (kb & 3) * STAGE_BYTES, bar = sb + OFF_BAR + 8 * (B_FULL1 + (kb & 3));
  const int r = b >> 3, hg = b & 7, slab = kb - KV_KB;
  const bool kv = slab >= 0 && slab < 5;
  const uint32_t kbar = sb + OFF_BAR + 8 * (B_KV + slab), dst = sb + OFF_KVS + slab * KVS_BYTES;
  mbar_expect_tx(bar, STAGE_BYTES);
  if (kv) mbar_expect_tx(kbar, KVS_BYTES);
  tma_3d(st, &m.x, 64 * kb, 64 * r, 0, bar);
  if (kv && KV_MIX) tma_3d(dst, &m.k, 0, 32 * (b >> 1) - 3, 2 * slab + (b & 1), kbar);
  tma_3d(st + ST_W, &m.wm, 80 * hg + (tail_first(hg) ? 16 : 0), 64 * kb, 0, bar);
  if (kv && KV_MIX) tma_3d(dst + KVS_V, &m.v, 0, 32 * (b >> 1), 2 * slab + (b & 1), kbar);
  tma_3d(st + ST_WT, &m.wt, 80 * hg + (tail_first(hg) ? 0 : 64), 64 * kb, 0, bar);
  if (kv && !KV_MIX) tma_3d(dst, &m.k, 0, 32 * (b >> 1) - 3, 2 * slab + (b & 1), kbar);
  if (kv && !KV_MIX) tma_3d(dst + KVS_V, &m.v, 0, 32 * (b >> 1), 2 * slab + (b & 1), kbar);
}

__global__ void __launch_bounds__(NTHR, 1) fused_kernel(const __grid_constant__ Maps m, const Params p) {
  extern __shared__ __align__(1024) uint8_t smem[];
  const uint32_t sb = (uint32_t)__cvta_generic_to_shared(smem);
  const uint32_t bars = sb + OFF_BAR;
  const int tid = threadIdx.x, lane = tid & 31;
  int b = blockIdx.x;
  if (BMAP == 1) b = (((b & 63) >> 3) * 2 + (b & 1)) * 8 + (((b < 64 ? 0x6521 : 0x7430) >> (4 * ((b >> 1) & 3))) & 7);
  if (BMAP == 2) b = ((b & 63) >> 2) * 8 + (((b < 64 ? 0x6521 : 0x7430) >> (4 * (b & 3))) & 7);
  if (BMAP == 3) b = (((b & 63) >> 3) * 2 + (b & 1)) * 8 + (((b < 64 ? 0x7430 : 0x6521) >> (4 * ((b >> 1) & 3))) & 7);
  if (BMAP == 4) b = (((b >> 4) * 2 + (b & 1)) * 8) + ((b >> 1) & 7);
  if (BMAP == 5) b = 127 - b;
  const int r = b >> 3, hg = b & 7;

  if (tid == T_ISSUE) {
    TSM(true, 0);
#pragma unroll
    for (int i = 0; i < 4; i++) mbar_init(bars + 8 * (B_FULL1 + i), 1);
#pragma unroll
    for (int i = 0; i < 3; i++) mbar_init(bars + 8 * (B_KV + i), 1);
    fence_async_smem();
#pragma unroll 1
    for (int kb = 0; kb <= PRE2; kb++) load_stage(sb, kb, b, m);
  } else if (tid >= T_PF && tid < T_PF + 12) {
    tm_prefetch(&m.x + (tid - T_PF));
  } else if (tid == T_INIT) {
#pragma unroll
    for (int i = 0; i < 4; i++) mbar_init(bars + 8 * (B_EMPTY1 + i), 8);
#pragma unroll
    for (int i = 0; i < 8; i++) mbar_init(bars + 8 * (B_FULL2 + i), 1);
#pragma unroll
    for (int i = 0; i < 4; i++) mbar_init(bars + 8 * (B_EMPTY2 + i), 8);
#pragma unroll
    for (int i = 0; i < 4; i++) mbar_init(bars + 8 * (B_U + i), 1);
    mbar_init(bars + 8 * B_HA, 4);
    mbar_init(bars + 8 * B_GATE, 4);
    mbar_init(bars + 8 * B_HB, 1);
    mbar_init(bars + 8 * B_KVD, 4);
    mbar_init(bars + 8 * B_QF, 1);
    mbar_init(bars + 8 * B_ATTN, 8);
    mbar_init(bars + 8 * B_ATT2, 8);
    mbar_init(bars + 8 * B_P1, 8);
    mbar_init(bars + 8 * B_C34, 1);
    mbar_init(bars + 8 * B_YRB, 1);
#pragma unroll
    for (int i = 0; i < 5; i++) mbar_init(bars + 8 * (B_YST + i), 4);
#pragma unroll
    for (int i = 0; i < 5; i++) mbar_init(bars + 8 * (B_US + i), U_TMA ? 4 : i == 2 ? 20 : 1);
    mbar_init(bars + 8 * B_YSIG, 1);
    mbar_init(bars + 8 * B_YFULL, 1);
    mbar_init(bars + 8 * B_EPOCH, 1);
    mbar_init(bars + 8 * B_PREP, 4);
    mbar_init(bars + 8 * B_USIG, 1);
    mbar_init(bars + 8 * B_WST, 1);
#pragma unroll
    for (int i = 3; i < 5; i++) mbar_init(bars + 8 * (B_KV + i), 1);
    mbar_init(bars + 8 * B_E3, 8);
    mbar_init(bars + 8 * B_LAST, 1);
    mbar_init(bars + 8 * B_OSIG, 1);
    mbar_init(bars + 8 * B_WOP, 1);
    fence_async_smem();
  }
  const int warp = __shfl_sync(0xffffffffu, tid >> 5, 0), wg = warp >> 2, w = warp & 3;
  __syncthreads();

  if (wg == 3) {
    asm volatile("setmaxnreg.dec.sync.aligned.u32 56;");
    if (w == 0) {
      if (lane == 0) {
#pragma unroll 1
        for (int kb = 1 + PRE2; kb < 10; kb++) {
          if (kb >= 4) mbar_wait(bars + 8 * (kb == 7 ? B_E3 : B_EMPTY1 + (kb & 3)), (kb >> 3) & 1);
          TSIF(kb >= 4, 44 + kb);
          load_stage(sb, kb, b, m);
          TSIF(kb == 3, 60);
          if (kb == TRIG_KB) mbar_arrive(bars + 8 * B_LAST);
        }
        mbar_wait(bars + 8 * B_WOP, 0);
        mbar_wait(bars + 8 * WL_TRIG, 0);
        mbar_wait(bars + 8 * B_EPOCH, 0);
        flag_wait(g_cnt + C_W + 32 * hg, (lds32(sb + OFF_EPOCH) + 1) * 16);
        TS(30);
#pragma unroll 1
        for (int j = 0; j < 8; j++) {
          if (j >= 6) mbar_wait(bars + 8 * (B_EMPTY2 + j - 6), 0);
          if (j == 4) mbar_wait(bars + 8 * B_ATTN, 0);
          TSIF(j >= 6, 100 + j);
          if (RF_GATE && j == 6) mbar_wait(bars + 8 * B_YSIG, 0);
          mbar_expect_tx(bars + 8 * (B_FULL2 + j), j == 0 ? WO_BYTES : j == 5 ? O_BYTES + WO_BYTES + 512 : O_BYTES + WO_BYTES);
          bulk_load(sb + off_w(j), g_WO + (hg * 8 + step_src(hg, j)) * 800, WO_BYTES, bars + 8 * (B_FULL2 + j));
        }
        mbar_wait(bars + 8 * (B_EMPTY2 + Q_SLOT), 0);
        mbar_expect_tx(bars + 8 * B_QF, O_BYTES);
        tma_2d(sb + OFF_QS, &m.qm, 80 * hg, 128 * r, bars + 8 * B_QF);
        if (!QBOX) tma_2d(sb + OFF_QT, &m.qt, 80 * hg + 64, 128 * r, bars + 8 * B_QF);
      }
    } else if (w == 1) {
      unsigned epoch = 0;
      if (lane == 0) {
        epoch = atomicAdd(g_cnt + C_LAUNCH, 1u) / NCTA;
        asm volatile("st.shared.u32 [%0], %1;" ::"r"(sb + OFF_EPOCH), "r"(epoch) : "memory");
        mbar_arrive(bars + 8 * B_EPOCH);
        mbar_wait(bars + 8 * B_KVD, 0);
        mbar_expect_tx(bars + 8 * B_HB, 5 * 4096);
#pragma unroll 1
        for (int c = 0; c < 5; c++) {
          if (c == 3) mbar_wait(bars + 8 * B_S3, 0);
          bulk_load(sb + off_ch(c) + U_BYTES, p.ssm_k + (5 * b + c) * SEQ, 4096, bars + 8 * B_HB);
        }
#pragma unroll
        for (int c = 0; c < 4; c++) mbar_expect_tx(bars + 8 * (B_U + c), c < 3 ? U_BYTES : 2 * U_BYTES);
        const uint4* usrc = g_U + 5 * b * U_PITCH;
        mbar_wait(bars + 8 * B_USIG, 0);
        flag_wait(g_cnt + C_PREP + 32 * (b & 15), (epoch + 1) * NCTA);
        TS(23);
#pragma unroll
        for (int c = 0; c < 5; c++) {
          if (c == 3 && U_TRIM) mbar_wait(bars + 8 * (B_U + 2), 0);
          bulk_load(sb + off_ch(c), usrc + c * U_PITCH, U_BYTES, bars + 8 * (B_U + (c < 3 ? c : 3)));
          TSIF(c == 0 || c == 4, 116 + (c >> 2));
        }
      }
      epoch = __shfl_sync(0xffffffffu, epoch, 0);
      if (lane < 8) {
        const int src = (b & ~7) | step_src(hg, lane);
        mbar_wait(bars + 8 * OP_TRIG, 0);
        TS(20);
        bool seen = false;
#pragma unroll 1
        for (int spins = 0; spins < SPIN_LIMIT; spins++) {
          const bool now = !seen && (int)(flag_read(g_cnt + C_O + 32 * src) - (epoch + 1)) >= 0;
          if (now && lane >= 1 && lane < 4) bulk_load(sb + off_o(lane), g_O + src * 1280, O_BYTES, bars + 8 * (B_FULL2 + lane));
          seen = seen || now;
          if (__all_sync(0xff, seen)) break;
        }
        TS(21);
        if (lane == 5) bulk_load(sb + OFF_GATE, g_gate + 128 * r, 512, bars + 8 * (B_FULL2 + 5));
#pragma unroll 1
        for (int j = 4; j < 8; j++) {
          if (lane == j) {
            mbar_wait(bars + 8 * (j < 6 ? B_C34 : B_EMPTY2 + j - 6), 0);
            if (RF_GATE && j == 6) mbar_wait(bars + 8 * B_YSIG, 0);
            bulk_load(sb + off_o(j), g_O + src * 1280, O_BYTES, bars + 8 * (B_FULL2 + j));
          }
          __syncwarp(0xff);
        }
        TS(22);
      }
    } else if (w == 2) {
      mbar_wait(bars + 8 * B_PREP, 0);
      flag_signal(g_cnt + C_PREP, 16, lane);
      TS(25);
      if (lane == 0) mbar_arrive(bars + 8 * B_USIG);
      mbar_wait(bars + 8 * B_GATE, 0);
      if (G_TMA) {
        if (lane == 0) {
          asm volatile("cp.async.bulk.global.shared::cta.bulk_group [%0], [%1], 64;\ncp.async.bulk.commit_group;\n"
                       "cp.async.bulk.wait_group.read 0;" ::"l"(g_gate + 16 * b), "r"(sb + OFF_GATE + 64 * hg) : "memory");
          bulk_load(sb + OFF_GATE + 64 * hg, g_gate + 16 * b, 64, bars + 8 * B_ORB);
        }
      } else if (((NOMB & 1) || O_RB) && lane == 0) {
        asm volatile("fence.release.gpu;" ::: "memory");
      }
      mbar_wait(bars + 8 * B_ATTN, 0);
      if (lane == 0) {
        if (O_DEFER) mbar_wait(bars + 8 * (B_U + 3), 0);
        asm volatile("cp.async.bulk.global.shared::cta.bulk_group [%0], [%1], 20480;\ncp.async.bulk.commit_group;"
                     ::"l"(g_O + b * 1280), "r"(sb + OFF_OA) : "memory");
        if (O_RB == 2) {
          asm volatile("cp.async.bulk.wait_group.read 0;" ::: "memory");
          mbar_expect_tx(bars + 8 * B_ORB, O_BYTES + 64 * G_TMA);
          bulk_load(sb + OFF_OA, g_O + b * 1280, O_BYTES, bars + 8 * B_ORB);
          mbar_wait(bars + 8 * B_ORB, 0);
          flag_bump(g_cnt + C_O + 32 * b);
        } else if (O_RB) asm volatile("cp.async.bulk.wait_group.read 0;" ::: "memory");
        else asm volatile("cp.async.bulk.wait_group 0;\nfence.proxy.async.global;" ::: "memory");
      }
      TS(74);
      if (O_RB == 2) {
      } else if (O_RB) {
        __syncwarp();
        unsigned v[5];
#pragma unroll
        for (int c = 0; c < 5; c++) v[c] = flag_read(reinterpret_cast<const unsigned*>(g_O + b * 1280 + 256 * c + 8 * lane + 7));
        const unsigned dep = __reduce_or_sync(0xffffffffu, (v[0] ^ v[1] ^ v[2] ^ v[3] ^ v[4]) & p.zero);
        if (lane == 0) flag_bump(g_cnt + C_O + 32 * b + dep);
      } else if (!(NOMB & 1)) flag_signal(g_cnt + C_O + 32 * b, 1, lane);
      else if (lane == 0) flag_bump(g_cnt + C_O + 32 * b);
      TS(26);
      if (lane == 0) mbar_arrive(bars + 8 * B_OSIG);

    } else {
      if (lane == 0) {
        uint4* dst = g_WO + (hg * 8 + (r >> 1)) * 800 + (r & 1) * 80;
        if (WPF) {
          mbar_wait(bars + 8 * WPF, 0);
          if (WPF_LIN)
            asm volatile("cp.async.bulk.prefetch.L2.global [%0], 6400;" ::"l"(p.wo + b * 3200) : "memory");
          else
            asm volatile("cp.async.bulk.prefetch.tensor.3d.L2.global [%0, {%1, %2, %3}];" ::"l"(&m.wo), "r"(0), "r"(40 * r), "r"(5 * hg) : "memory");
        }
        mbar_wait(bars + 8 * B_P1, 0);
        mbar_wait(bars + 8 * WB_TRIG, 0);
        mbar_expect_tx(bars + 8 * B_WST, WO_BYTES / 2);
        tma_3d(sb + OFF_WS, &m.wo, 0, 40 * r, 5 * hg, bars + 8 * B_WST);
        mbar_wait(bars + 8 * B_WST, 0);
        mbar_wait(bars + 8 * WO_TRIG, 0);
#pragma unroll 1
        for (int n = 0; n < 5; n++)
          asm volatile("cp.async.bulk.global.shared::cta.bulk_group [%0], [%1], 1280;" ::"l"(dst + 160 * n), "r"(sb + OFF_WS + 1280 * n) : "memory");
        if (W_RB) {
          asm volatile("cp.async.bulk.commit_group;\ncp.async.bulk.wait_group.read 0;" ::: "memory");
          mbar_expect_tx(bars + 8 * B_WST, WO_BYTES / 2);
#pragma unroll 1
          for (int n = 0; n < 5; n++) bulk_load(sb + OFF_WS + 1280 * n, dst + 160 * n, 1280, bars + 8 * B_WST);
          mbar_wait(bars + 8 * B_WST, 1);
        } else {
          asm volatile("cp.async.bulk.commit_group;\ncp.async.bulk.wait_group 0;\nfence.proxy.async.global;" ::: "memory");
          if (!(NOMB & 4)) asm volatile("fence.release.gpu;" ::: "memory");
        }
        flag_bump(g_cnt + C_W + 32 * hg);
        mbar_arrive(bars + 8 * B_WOP);
        TS(71);
        mbar_expect_tx(bars + 8 * B_C34, 3 * U_BYTES);
        mbar_expect_tx(bars + 8 * B_YRB, 2 * U_BYTES);
#pragma unroll 1
        for (int c = 0; c < 5; c++) {
          mbar_wait(bars + 8 * (B_YST + c), 0);
          asm volatile("cp.async.bulk.global.shared::cta.bulk_group [%0], [%1], 4096;\ncp.async.bulk.commit_group;\n"
                       "cp.async.bulk.wait_group.read 0;" ::"l"(g_Y + (5 * b + c) * Y_PITCH), "r"(sb + off_ch(c)) : "memory");
          bulk_load(sb + off_ch(c), g_Y + (5 * b + c) * Y_PITCH, U_BYTES, bars + 8 * (c < 3 ? B_C34 : B_YRB));
        }
        TS(75);
        mbar_wait(bars + 8 * B_C34, 0);
        mbar_wait(bars + 8 * B_YRB, 0);
        flag_bump(g_cnt + C_Y + 32 * (b >> 4));
        TS(27);
        mbar_arrive(bars + 8 * B_YSIG);
        mbar_expect_tx(bars + 8 * B_YFULL, 20480);
        flag_wait(g_cnt + C_Y + 32 * hg, (lds32(sb + OFF_EPOCH) + 1) * 16);
        TS(24);
        tma_2d(sb + OFF_YT, &m.y, 128 * r, 80 * hg, bars + 8 * B_YFULL);
        tma_2d(sb + OFF_YT + 10240, &m.y, 128 * r + 64, 80 * hg, bars + 8 * B_YFULL);
      }
    }
  } else {
    asm volatile("setmaxnreg.inc.sync.aligned.u32 152;");
    if (wg < 2) {
      float acc[120];
#pragma unroll
      for (int i = 0; i < 120; i++) acc[i] = 0.f;
      const uint32_t da = desc_lo(sb + wg * 8192, 16), db = desc_lo(sb + ST_W, 8192), dc = desc_lo(sb + ST_WT, 2048);
      if (PW1) pin<120>(acc);
      if (PW1 == 2) mbar_wait(bars + 8 * B_FULL1, 0);
#pragma unroll 1
      for (int kb = 0; kb < 10; kb++) {
        mbar_wait(bars + 8 * (B_FULL1 + (kb & 3)), (kb >> 2) & 1);
        const uint32_t so = (kb & 3) * (STAGE_BYTES >> 4);
        wg_fence();
#pragma unroll
        for (int k = 0; k < 4; k++) {
          WgSST<192>::mma<HI_SW128, HI_SW128>(acc, da + so + 2 * k, db + so + 128 * k, 1);
          WgSST<48>::mma<HI_SW128, HI_SW32>(acc + 96, da + so + 2 * k, dc + so + 32 * k, 1);
        }
        wg_commit();
        wg_wait<1>();
        if (kb > 0 && lane == 0) mbar_arrive(bars + 8 * (kb == 4 ? B_E3 : B_EMPTY1 + ((kb - 1) & 3)));
      }
      mbar_wait(bars + 8 * B_EPOCH, 0);
      const uint32_t tag = lds32(sb + OFF_EPOCH) + 1;
      mbar_wait(bars + 8 * B_S3, 0);
      wg_wait<0>();
      pin<120>(acc);
      if (lane == 0) mbar_arrive(bars + 8 * B_P1);
      TSM(w == 0, 3 + wg);
      attention(acc, sb, b, wg, w, lane, tag, p.zero);
    } else {
      const int tw = tid & 127, chl = 64 * (b & 1) + 8 * w + (lane >> 2);
      uint4* up = g_U + chl * U_PITCH + ((4 * (b >> 1) + (lane & 3)) ^ ((b >> 2) & 1));
      uint2 sw[10];
      uint32_t dv = 0;
      if (lane < 5) dv = __ldg(reinterpret_cast<const unsigned short*>(p.ssm_D) + 5 * b + lane);
#pragma unroll
      for (int i = 0; i < 10; i++) sw[i] = ldg64(reinterpret_cast<const uint2*>(p.shift_k) + chl + 128 * (i >> 1) + 32 * (i & 1));
      uint32_t tab[12];
      uint32_t tt[2];
      fft_tables(tab, tw);
      fft_twiddles(tt, tw);
      uint4 res[10];
#pragma unroll
      for (int i = 0; i < 10; i++) res[i] = make_uint4(0, 0, 0, 0);
#pragma unroll 1
      for (int slab = 0; slab < 5; slab++) {
#pragma unroll
        for (int i = 0; i < 8; i++) res[i] = res[i + 2];
        prep_slab(res + 8, sw, sb, slab, w, lane);
        TSIF(w == 0, 99 + 4 * slab);
#pragma unroll
        for (int i = 0; i < 8; i++) sw[i] = sw[i + 2];
      }
      TSIF(w == 0, 28);
      __syncwarp();
      if (lane == 0) mbar_arrive(bars + 8 * B_KVD + ((res[8].x ^ res[9].x) & p.zero));
      mbar_wait(bars + 8 * B_KVD, 0);
      fft_tables_store(tab, sb, tw);
      mbar_wait(bars + 8 * B_LAST, 0);
#pragma unroll
      for (int i = 0; i < 10; i++) up[(128 * (i >> 1) + 32 * (i & 1)) * U_PITCH] = res[i];
      __syncwarp();
      if (lane == 0) mbar_arrive(bars + 8 * B_PREP);
      TSIF(w == 0 && !U_TMA, 5);
      mbar_wait(bars + 8 * (G_AFTER ? B_USIG : B_LAST), 0);
      prep_gate(p, sb, b, w, lane);
      __syncwarp();
      if (lane == 0) mbar_arrive(bars + 8 * B_GATE);
      TSIF(w == 0, 72);
      mbar_wait(bars + 8 * B_HB, 0);
      TSIF(w == 0, 2);
      const uint32_t ha = sb + U_BYTES + ((tw >> 3) * 16 + 8 + (tw & 7)) * 16;
      uint4 hv[5];
#pragma unroll
      for (int c = 0; c < 5; c++) hv[c] = lds128(ha + off_ch(c));
      __syncwarp();
#pragma unroll
      for (int c = 0; c < 5; c++) sts128((ha ^ 16) + off_ch(c), hv[c].x, hv[c].y, hv[c].z, hv[c].w);
      asm volatile("st.shared.v2.u32 [%0], {%1, %2};" ::"r"(sb + OFF_TT + 8 * tw), "r"(tt[0]), "r"(tt[1]) : "memory");
      if (tw < 5) asm volatile("st.shared.f32 [%0], %1;" ::"r"(sb + OFF_D + 4 * tw), "f"(bf_lo(dv) * 0.125f) : "memory");
      fence_async_smem();
      __syncwarp();
      if (lane == 0) mbar_arrive(bars + 8 * B_HA);
      TSIF(w == 0, 6);
    }

    FftConst fc;
    TSM(w == 0 && wg == 0, 104);
    mbar_wait(bars + 8 * B_HA, 0);
    fft_matrices(fc, sb, w, lane);
    TSM(w == 0 && wg == 0, 105);
    TSM(w == 0 && wg == 2, 124);
#pragma unroll 1
    for (uint32_t tasks = wg == 0 ? TASK0 : wg == 1 ? TASK1 : TASK2; tasks; tasks >>= 4) {
      const int c = (tasks & 7) - 1;
      conv_channel(fc, sb, c, wg, w, lane);
      if (lane == 0) mbar_arrive(bars + 8 * (B_YST + c));
      TSM(w == 0, 10 + c);
    }

    if (wg < 2) {
      const int g = lane >> 2;
      float acc[40];
#pragma unroll
      for (int i = 0; i < 40; i++) acc[i] = 0.f;
      const uint32_t da = desc_lo(sb + wg * 1024, 2048), db = desc_lo(sb, 2560);
      mbar_wait(bars + 8 * (O_RB == 2 ? B_ORB : B_ATTN), 0);
      if (PW2) mbar_wait(bars + 8 * B_FULL2, 0);
      mbar_wait(bars + 8 * B_CVD, 0);
      TSM(w == 0, 15 + wg);
#pragma unroll 1
      for (int j = 0; j < 8; j++) {
        mbar_wait(bars + 8 * (B_FULL2 + j), 0);
        TSM(w == 0 && wg == 0, 44 + (j < 4 ? j : j + 6));
        const uint32_t oa = da + (off_o(j) >> 4), ob = db + (off_w(j) >> 4);
        wg_fence();
#pragma unroll
        for (int k = 0; k < 5; k++) WgSST<80>::mma<HI_NONE, HI_SW32>(acc, oa + 256 * k, ob + 32 * k, 1);
        wg_commit();
        wg_wait<1>();
        if (j >= 1 && j <= Q_SLOT + 1 && lane == 0) mbar_arrive(bars + 8 * (B_EMPTY2 + j - 1));
      }
      TSIF(w == 0 && wg == 0, 113);
      const int tr = 64 * wg + 16 * w + (lane & 15);
      const uint32_t fm = sb + OFF_QS + tr * 128, fx = (lane >> 4) ^ (tr & 7), fq = sb + OFF_QS + tr * 160 + (lane >> 4) * 16;
      const uint32_t ft = sb + OFF_QT + tr * 32 + (((lane >> 4) ^ (tr >> 2)) & 1) * 16;
      const float g0 = __uint_as_float(lds32(sb + OFF_GATE + (64 * wg + 16 * w + g) * 4));
      const float g1 = __uint_as_float(lds32(sb + OFF_GATE + (64 * wg + 16 * w + 8 + g) * 4));
      const uint32_t ga = pack2(g0, g0), gb = pack2(g1, g1);
      const uint32_t na = pack2(1.f - g0, 1.f - g0), nb = pack2(1.f - g1, 1.f - g1);

      uint32_t qf[20];
      mbar_wait(bars + 8 * B_QF, 0);
      TSM(w == 0 && wg == 0, 99);
#pragma unroll
      for (int j = 0; j < 5; j++) ldsm4(qf + 4 * j, QBOX ? fq + 32 * j : j < 4 ? fm + ((fx ^ (2 * j)) << 4) : ft);
      if (FUSE_MIX) {
#pragma unroll
        for (int i = 0; i < 20; i++) {
          qf[i] = bmul((i & 1) ? gb : ga, qf[i]);
          asm volatile("" : "+r"(qf[i]));
        }
      }
      wg_wait<0>();
      pin<40>(acc);
      TSM(w == 0, 17 + wg);
      uint32_t pb[20];
#pragma unroll
      for (int j = 0; j < 10; j++) {
        pb[2 * j] = bmul(na, pack2(acc[4 * j], acc[4 * j + 1]));
        pb[2 * j + 1] = bmul(nb, pack2(acc[4 * j + 2], acc[4 * j + 3]));
        asm volatile("" : "+r"(pb[2 * j]), "+r"(pb[2 * j + 1]));
      }
      const uint32_t ya = sb + OFF_YT + wg * 10240 + ((lane >> 4) * 8 + (lane & 7)) * 128 +
                          (((2 * w + (((lane >> 3) & 1) ^ wg)) ^ (lane & 7)) << 4);
      mbar_wait(bars + 8 * B_YFULL, 0);
      TSM(w == 0 && wg == 0, 19);
#pragma unroll
      for (int j = 0; j < 5; j++) {
        uint32_t y[4];
        ldsm4t(y, ya + 2048 * j);
#pragma unroll
        for (int i = 0; i < 4; i++)
          qf[4 * j + i] = FUSE_MIX ? bfma(qf[4 * j + i], y[i], pb[4 * j + i]) : badd(bmul((i & 1) ? gb : ga, bmul(qf[4 * j + i], y[i])), pb[4 * j + i]);
      }
#pragma unroll
      for (int j = 0; j < 5; j++) stsm4(QBOX ? fq + 32 * j : j < 4 ? fm + ((fx ^ (2 * j)) << 4) : ft, qf + 4 * j);
      fence_async_smem();
      __syncwarp();
      if (lane == 0) {
        const int row = 64 * wg + 16 * w;
        asm volatile("cp.async.bulk.tensor.2d.global.shared::cta.bulk_group [%0, {%2, %3}], [%1];"
                     ::"l"(&m.om), "r"(sb + OFF_QS + row * (QBOX ? 160 : 128)), "r"(80 * hg), "r"(128 * r + row) : "memory");
        if (!QBOX) asm volatile("cp.async.bulk.tensor.2d.global.shared::cta.bulk_group [%0, {%2, %3}], [%1];"
                     ::"l"(&m.ot), "r"(sb + OFF_QT + row * 32), "r"(80 * hg + 64), "r"(128 * r + row) : "memory");
        asm volatile("cp.async.bulk.commit_group;\ncp.async.bulk.wait_group.read 0;" ::: "memory");
      }
      TSM(w == 0 || w == 3, 40 + 2 * wg + (w & 1));
      if (ENDBAR) asm volatile("bar.sync 15, 256;" ::: "memory");
    }
  }
}

typedef CUresult (*EncodeFn)(CUtensorMap*, CUtensorMapDataType, cuuint32_t, void*, const cuuint64_t*, const cuuint64_t*,
                             const cuuint32_t*, const cuuint32_t*, CUtensorMapInterleave, CUtensorMapSwizzle,
                             CUtensorMapL2promotion, CUtensorMapFloatOOBfill);

void encode(EncodeFn fn, CUtensorMap* tm, const void* base, int rank, const cuuint64_t* dims, const cuuint64_t* strides,
            const cuuint32_t* box, CUtensorMapSwizzle swz) {
  const cuuint32_t ones[3] = {1, 1, 1};
  fn(tm, CU_TENSOR_MAP_DATA_TYPE_BFLOAT16, rank, const_cast<void*>(base), dims, strides, box, ones,
     CU_TENSOR_MAP_INTERLEAVE_NONE, swz, CU_TENSOR_MAP_L2_PROMOTION_L2_128B, CU_TENSOR_MAP_FLOAT_OOB_FILL_NONE);
}

}

extern "C" void kernel_launch(void* const* d_in, const int* in_sizes, int n_in, void* d_out, int out_size) {
  (void)in_sizes; (void)n_in; (void)out_size;
  Params p;
  p.q = (const __nv_bfloat16*)d_in[0];
  p.k = (const __nv_bfloat16*)d_in[1];
  p.v = (const __nv_bfloat16*)d_in[2];
  p.shift_k = (const __nv_bfloat16*)d_in[3];
  p.ssm_k = (const __nv_bfloat16*)d_in[4];
  p.ssm_D = (const __nv_bfloat16*)d_in[5];
  p.wqkv = (const __nv_bfloat16*)d_in[7];
  p.wo = (const __nv_bfloat16*)d_in[8];
  p.gate_w = (const __nv_bfloat16*)d_in[9];
  p.out = (__nv_bfloat16*)d_out;
  p.zero = 0;

  static EncodeFn fn = nullptr;
  static void *yaddr = nullptr, *uaddr = nullptr;
  if (!fn) {
    cudaDriverEntryPointQueryResult qr;
    void* f = nullptr;
    cudaGetDriverEntryPoint("cuTensorMapEncodeTiled", &f, cudaEnableDefault, &qr);
    fn = (EncodeFn)f;
    cudaGetSymbolAddress(&yaddr, g_Y);
    cudaGetSymbolAddress(&uaddr, g_U);
    cudaFuncSetAttribute(fused_kernel, cudaFuncAttributeMaxDynamicSharedMemorySize, SMEM_BYTES);
  }
  Maps m;
  {
    const cuuint64_t dims[3] = {640, 1024, 2}, st[2] = {2560, 1280};
    const cuuint32_t box[3] = {64, 64, 2};
    encode(fn, &m.x, p.q, 3, dims, st, box, CU_TENSOR_MAP_SWIZZLE_128B);
  }
  {
    const cuuint64_t dims[3] = {640, 640, 3}, st[2] = {3840, 1280};
    const cuuint32_t box[3] = {64, 64, 3}, boxt[3] = {16, 64, 3};
    encode(fn, &m.wm, p.wqkv, 3, dims, st, box, CU_TENSOR_MAP_SWIZZLE_128B);
    encode(fn, &m.wt, p.wqkv, 3, dims, st, boxt, CU_TENSOR_MAP_SWIZZLE_32B);
  }
  {
    const cuuint64_t dims[3] = {64, 2048, 10}, st[2] = {1280, 128};
    const cuuint32_t boxk[3] = {64, 35, 1}, boxv[3] = {64, 32, 1};
    encode(fn, &m.k, p.k, 3, dims, st, boxk, CU_TENSOR_MAP_SWIZZLE_128B);
    encode(fn, &m.v, p.v, 3, dims, st, boxv, CU_TENSOR_MAP_SWIZZLE_128B);
  }
  {
    const cuuint64_t dims[3] = {16, 640, 40}, st[2] = {1280, 32};
    const cuuint32_t box[3] = {16, 40, 5};
    encode(fn, &m.wo, p.wo, 3, dims, st, box, CU_TENSOR_MAP_SWIZZLE_32B);
  }
  {
    const cuuint64_t dims[2] = {2048, 640}, st[1] = {Y_PITCH * 16};
    const cuuint32_t box[2] = {64, 80};
    encode(fn, &m.y, yaddr, 2, dims, st, box, CU_TENSOR_MAP_SWIZZLE_128B);
    const cuuint64_t stu[1] = {U_PITCH * 16};
    const cuuint32_t boxu[2] = {32, 64};
    encode(fn, &m.u, uaddr, 2, dims, stu, boxu, CU_TENSOR_MAP_SWIZZLE_NONE);
  }
  {
    const cuuint64_t dims[2] = {640, 2048}, st[1] = {1280};
    const cuuint32_t bqm[2] = {QBOX ? 80 : 64, 128}, bqt[2] = {16, 128}, bom[2] = {QBOX ? 80 : 64, 16}, bot[2] = {16, 16};
    encode(fn, &m.qm, p.q, 2, dims, st, bqm, QBOX ? CU_TENSOR_MAP_SWIZZLE_NONE : CU_TENSOR_MAP_SWIZZLE_128B);
    encode(fn, &m.qt, p.q, 2, dims, st, bqt, CU_TENSOR_MAP_SWIZZLE_32B);
    encode(fn, &m.om, p.out, 2, dims, st, bom, QBOX ? CU_TENSOR_MAP_SWIZZLE_NONE : CU_TENSOR_MAP_SWIZZLE_128B);
    encode(fn, &m.ot, p.out, 2, dims, st, bot, CU_TENSOR_MAP_SWIZZLE_32B);
  }
  fused_kernel<<<NCTA, NTHR, SMEM_BYTES>>>(m, p);
}
```

```cpp
#include <cuda.h>
#include <cuda_bf16.h>
#include <cuda_runtime.h>
#include <stdint.h>

namespace {

constexpr int SEQ = 2048, DIM = 640, NCTA = 128, NTHR = 512;

#define TRIG_KB 9
#define KV_KB 2
#define DEV_EXIT 0
#define ATT_GATE 0
#define G_AFTER 0
#define FENCE_LO 0
#define FENCE_HI 0
#define PW1 2
#define PW2 1
#define ENDBAR 0
#define PAD_KB 0
#define Y_ALIAS 1
#define NOMB 0
#define SRC_ROT 0
#define WAIT_NS 0
#define WB_TRIG B_USIG
#define G_POS 0
#define TAILF 1
#define T_ISSUE 384
#define T_PF 416
#define T_INIT 448
#define ATT_MERGE 0
#define BMAP 1
#define PRE2 1
#define KV_MIX 0
#define O_DEFER 0
#define TASK0 0x52
#define TASK1 0x3
#define TASK2 0x41
#define HALO_FIRST 1
#define PREV_EARLY 0
#define Y_RB 2
#define O_RB 2
#define O_EAGER 1
#define OP_TRIG B_ATTN
#define FUSE_MIX 1
#define Q_EARLY 1
#define U_TRIM 1
#define Q_SLOT 3
#define G_TMA 1
#define W_RB 1
#define WPF B_S3
#define WPF_LIN 1
#define QBOX 0
#define ACQ 0
#define U_TMA 0
#define U_GATE 0
#define RF_GATE 0
#define WO_TRIG B_WST
#define WL_TRIG B_WOP
#define WO_GATE 4

constexpr uint32_t STAGE_BYTES = 47104, ST_W = 16384, ST_WT = 40960;
constexpr uint32_t O_BYTES = 20480, WO_BYTES = 12800;
constexpr uint32_t OFF_OA = 0;
constexpr uint32_t OFF_QS = Q_SLOT * O_BYTES, OFF_QT = OFF_QS + 16384;
constexpr uint32_t OFF_WC = 81920;
constexpr uint32_t OFF_WA = 94720;
constexpr uint32_t OFF_GATE = 145920;
constexpr uint32_t OFF_TT = 146432;
constexpr uint32_t OFF_KVX = 148480;
constexpr uint32_t OFF_CH3 = 163840;
constexpr uint32_t CH_BYTES = 12288, U_BYTES = 4096;
constexpr uint32_t OFF_FT = 225280, OFF_GT = 229376;
constexpr uint32_t OFF_CH0 = 188416;
constexpr uint32_t OFF_KVS = OFF_CH0, KVS_V = 4480, KVS_BYTES = 8576;
constexpr uint32_t OFF_WS = OFF_WA;
__device__ __forceinline__ uint32_t off_us(int s) { return OFF_CH0 + 4096 * ((0x65320 >> (4 * s)) & 7); }
constexpr uint32_t OFF_YT = 163840;
constexpr uint32_t OFF_BAR = 231936;
constexpr uint32_t SMEM_BYTES = OFF_BAR + 512;

enum : uint32_t {
  B_FULL1 = 0, B_EMPTY1 = 4, B_S3 = 7, B_FULL2 = 52, B_EMPTY2 = 13, B_U = 8, B_GATE = 12, B_HA = 19, B_HB = 20,
  B_ATTN = 21, B_C34 = 22, B_YRB = 23, B_YFULL = 24, B_EPOCH = 25, B_PREP = 26, B_P1 = 27, B_LAST = 28,
  B_E3 = 29, B_OSIG = 30, B_WOP = 31, B_USIG = 32, B_WST = 33, B_KV = 34, B_KVD = 39, B_QF = 17, B_ATT2 = 18, B_YST = 40,
  B_ORB = 45, B_CVD = 33 + 14, B_US = 45, B_YSIG = 50
};
constexpr uint32_t OFF_EPOCH = OFF_BAR + 8 * 51, OFF_D = OFF_BAR + 8 * 60;
__device__ __forceinline__ uint32_t off_o(int j) { return j < 4 ? OFF_OA + j * O_BYTES : j < 6 ? OFF_CH0 + (j - 4) * O_BYTES : OFF_OA + (j - 6) * O_BYTES; }
__device__ __forceinline__ uint32_t off_w(int j) { return j < 4 ? OFF_WA + j * WO_BYTES : j == 4 ? OFF_KVX : j == 5 ? OFF_WC : OFF_WA + (j - 6) * WO_BYTES; }
__device__ __forceinline__ int step_src(int hg, int j) {
  if (SRC_ROT == 2) {
    const int pos = (0x37621540 >> (4 * hg)) & 7;
    return j == 0 ? hg : (0x65217430 >> (4 * (j <= pos ? j - 1 : j))) & 7;
  }
  return SRC_ROT ? (hg + j) & 7 : j == 0 ? hg : j <= hg ? j - 1 : j;
}
__device__ __forceinline__ bool tail_first(int hg) { return TAILF && (hg & 3) == 3; }
__device__ __forceinline__ uint32_t off_ch(int c) { return (c < 3 ? OFF_CH0 : OFF_CH3 - 3 * CH_BYTES) + c * CH_BYTES; }

#define U_PITCH 264
__device__ __align__(1024) uint4 g_U[DIM * U_PITCH];
__device__ uint4 g_O[NCTA * 1280];
#define g_Y g_U
constexpr int Y_PITCH = U_PITCH;
__device__ uint4 g_WO[64 * 800];
__device__ uint4 g_halo[NCTA * 2 * 7 * 32];
__device__ __align__(128) float g_gate[SEQ + PAD_KB * 256];
__device__ unsigned g_cnt[32 * (1 + 2 * 16 + 8 + NCTA)];
constexpr int C_LAUNCH = 0, C_PREP = 32, C_Y = 32 * 17, C_W = 32 * 33, C_O = 32 * 41;

#define TSM(cond, slot) do { } while (0)
#define TSIF(cond, slot) do { if (__LINE__ >= FENCE_LO && __LINE__ < FENCE_HI) sched_fence(); } while (0)
__device__ __forceinline__ void sched_fence() {
  asm volatile("{\n.reg .pred p;\n.reg .u32 c;\nmov.u32 c, %%clock;\nsetp.eq.u32 p, c, 0;\n@p st.shared.u32 [%0], c;\n}"
               ::"r"(1024 + OFF_EPOCH + 4) : "memory");
}
#define TS(slot) TSIF(true, slot)

struct Params {
  const __nv_bfloat16 *q, *k, *v, *shift_k, *ssm_k, *ssm_D, *wqkv, *wo, *gate_w;
  __nv_bfloat16* out;
  uint32_t zero;
};

#define POLL_NS 0
constexpr int SPIN_LIMIT = 1 << 17;

__device__ __forceinline__ void mbar_init(uint32_t bar, uint32_t count) {
  asm volatile("mbarrier.init.shared::cta.b64 [%0], %1;" ::"r"(bar), "r"(count) : "memory");
}
__device__ __forceinline__ void mbar_expect_tx(uint32_t bar, uint32_t bytes) {
  asm volatile("mbarrier.arrive.expect_tx.shared::cta.b64 _, [%0], %1;" ::"r"(bar), "r"(bytes) : "memory");
}
__device__ __forceinline__ void mbar_arrive(uint32_t bar) {
  asm volatile("mbarrier.arrive.shared::cta.b64 _, [%0];" ::"r"(bar) : "memory");
}
__device__ __forceinline__ void mbar_wait(uint32_t bar, uint32_t parity) {
  uint32_t ok;
  int spins = 0;
  do {
    if (WAIT_NS)
      asm volatile("{\n.reg .pred p;\nmbarrier.try_wait.parity.shared::cta.b64 p, [%1], %2, %3;\nselp.b32 %0, 1, 0, p;\n}"
                   : "=r"(ok) : "r"(bar), "r"(parity), "r"(WAIT_NS) : "memory");
    else
      asm volatile("{\n.reg .pred p;\nmbarrier.try_wait.parity.shared::cta.b64 p, [%1], %2;\nselp.b32 %0, 1, 0, p;\n}"
                   : "=r"(ok) : "r"(bar), "r"(parity) : "memory");
    if (++spins > SPIN_LIMIT) break;
  } while (!ok);
}
__device__ __forceinline__ unsigned flag_read(const unsigned* p) {
  unsigned v;
  asm volatile("ld.relaxed.gpu.global.u32 %0, [%1];" : "=r"(v) : "l"(p) : "memory");
  return v;
}
__device__ __forceinline__ void flag_poll(const unsigned* p, unsigned target) {
  unsigned v;
  int spins = 0;
  do {
    if (POLL_NS && spins) __nanosleep(POLL_NS);
    asm volatile("ld.relaxed.gpu.global.u32 %0, [%1];" : "=r"(v) : "l"(p) : "memory");
    if (++spins > SPIN_LIMIT) break;
  } while ((int)(v - target) < 0);
}
__device__ __forceinline__ void flag_wait(const unsigned* p, unsigned target) {
  flag_poll(p, target);
  if (ACQ) asm volatile("fence.acquire.gpu;\nfence.proxy.async.global;" ::: "memory");
}
__device__ __forceinline__ void flag_signal(unsigned* p, int n, int lane) {
  if (lane == 0) asm volatile("fence.release.gpu;" ::: "memory");
  __syncwarp();
  if (lane < n) asm volatile("red.relaxed.gpu.global.add.u32 [%0], 1;" ::"l"(p + 32 * lane) : "memory");
}
__device__ __forceinline__ void flag_bump(unsigned* p) {
  asm volatile("red.relaxed.gpu.global.add.u32 [%0], 1;" ::"l"(p) : "memory");
}
__device__ __forceinline__ void fence_async_smem() { asm volatile("fence.proxy.async.shared::cta;" ::: "memory"); }
__device__ __forceinline__ void wg_sync(int id) { asm volatile("bar.sync %0, 128;" ::"r"(id) : "memory"); }

__device__ __forceinline__ void tma_2d(uint32_t dst, const CUtensorMap* tm, int c0, int c1, uint32_t bar) {
  asm volatile("cp.async.bulk.tensor.2d.shared::cluster.global.mbarrier::complete_tx::bytes [%0], [%1, {%3, %4}], [%2];"
               ::"r"(dst), "l"(tm), "r"(bar), "r"(c0), "r"(c1) : "memory");
}
__device__ __forceinline__ void tma_3d(uint32_t dst, const CUtensorMap* tm, int c0, int c1, int c2, uint32_t bar) {
  asm volatile("cp.async.bulk.tensor.3d.shared::cluster.global.mbarrier::complete_tx::bytes [%0], [%1, {%3, %4, %5}], [%2];"
               ::"r"(dst), "l"(tm), "r"(bar), "r"(c0), "r"(c1), "r"(c2) : "memory");
}
__device__ __forceinline__ void bulk_load(uint32_t dst, const void* src, uint32_t bytes, uint32_t bar) {
  asm volatile("cp.async.bulk.shared::cluster.global.mbarrier::complete_tx::bytes [%0], [%1], %2, [%3];"
               ::"r"(dst), "l"(src), "r"(bytes), "r"(bar) : "memory");
}
__device__ __forceinline__ void tm_prefetch(const CUtensorMap* tm) {
  asm volatile("prefetch.tensormap [%0];" ::"l"(tm) : "memory");
}

__device__ __forceinline__ void wg_fence() { asm volatile("wgmma.fence.sync.aligned;" ::: "memory"); }
__device__ __forceinline__ void wg_commit() { asm volatile("wgmma.commit_group.sync.aligned;" ::: "memory"); }
template <int N> __device__ __forceinline__ void wg_wait() { asm volatile("wgmma.wait_group.sync.aligned %0;" ::"n"(N) : "memory"); }
__device__ __forceinline__ uint32_t desc_lo(uint32_t addr, uint32_t lbo) { return ((addr & 0x3FFFF) >> 4) | ((lbo >> 4) << 16); }
constexpr uint32_t desc_hi(uint32_t sbo, uint32_t swz) { return (sbo >> 4) | (swz << 30); }
constexpr uint32_t HI_SW128 = desc_hi(1024, 1), HI_SW64 = desc_hi(512, 2), HI_SW32 = desc_hi(256, 3), HI_NONE = desc_hi(128, 0);
template <int N> __device__ __forceinline__ void pin(float* d) {
#pragma unroll
  for (int i = 0; i < N; i++) asm volatile("" : "+f"(d[i])::"memory");
}

__device__ __forceinline__ uint32_t lds32(uint32_t a) {
  uint32_t v;
  asm volatile("ld.volatile.shared.u32 %0, [%1];" : "=r"(v) : "r"(a) : "memory");
  return v;
}
__device__ __forceinline__ uint4 ldg128(const void* a) {
  uint4 v;
  asm volatile("ld.global.nc.v4.u32 {%0, %1, %2, %3}, [%4];" : "=r"(v.x), "=r"(v.y), "=r"(v.z), "=r"(v.w) : "l"(a) : "memory");
  return v;
}
__device__ __forceinline__ uint2 ldg64(const void* a) {
  uint2 v;
  asm volatile("ld.global.nc.v2.u32 {%0, %1}, [%2];" : "=r"(v.x), "=r"(v.y) : "l"(a) : "memory");
  return v;
}
__device__ __forceinline__ void ldsm4(uint32_t* r, uint32_t a) {
  asm volatile("ldmatrix.sync.aligned.m8n8.x4.shared.b16 {%0, %1, %2, %3}, [%4];"
               : "=r"(r[0]), "=r"(r[1]), "=r"(r[2]), "=r"(r[3]) : "r"(a) : "memory");
}
__device__ __forceinline__ void ldsm4t(uint32_t* r, uint32_t a) {
  asm volatile("ldmatrix.sync.aligned.m8n8.x4.trans.shared.b16 {%0, %1, %2, %3}, [%4];"
               : "=r"(r[0]), "=r"(r[1]), "=r"(r[2]), "=r"(r[3]) : "r"(a) : "memory");
}
__device__ __forceinline__ uint2 lds64(uint32_t a) {
  uint2 v;
  asm volatile("ld.shared.v2.u32 {%0, %1}, [%2];" : "=r"(v.x), "=r"(v.y) : "r"(a) : "memory");
  return v;
}
__device__ __forceinline__ uint4 lds128(uint32_t a) {
  uint4 v;
  asm volatile("ld.shared.v4.u32 {%0, %1, %2, %3}, [%4];" : "=r"(v.x), "=r"(v.y), "=r"(v.z), "=r"(v.w) : "r"(a) : "memory");
  return v;
}
__device__ __forceinline__ void sts128(uint32_t a, uint32_t x, uint32_t y, uint32_t z, uint32_t w) {
  asm volatile("st.shared.v4.u32 [%0], {%1, %2, %3, %4};" ::"r"(a), "r"(x), "r"(y), "r"(z), "r"(w) : "memory");
}
__device__ __forceinline__ void stsm4(uint32_t a, const uint32_t* r) {
  asm volatile("stmatrix.sync.aligned.m8n8.x4.shared.b16 [%0], {%1, %2, %3, %4};" ::"r"(a), "r"(r[0]), "r"(r[1]), "r"(r[2]), "r"(r[3]) : "memory");
}
__device__ __forceinline__ void stsm4t(uint32_t a, const uint32_t* r) {
  asm volatile("stmatrix.sync.aligned.m8n8.x4.trans.shared.b16 [%0], {%1, %2, %3, %4};" ::"r"(a), "r"(r[0]), "r"(r[1]), "r"(r[2]), "r"(r[3]) : "memory");
}
__device__ __forceinline__ uint32_t pack2(float lo, float hi) {
  uint32_t r;
  asm("cvt.rn.bf16x2.f32 %0, %1, %2;" : "=r"(r) : "f"(hi), "f"(lo));
  return r;
}
__device__ __forceinline__ uint32_t movm(uint32_t a) {
  uint32_t d;
  asm volatile("movmatrix.sync.aligned.m8n8.trans.b16 %0, %1;" : "=r"(d) : "r"(a));
  return d;
}
__device__ __forceinline__ uint32_t bmul(uint32_t a, uint32_t b) {
  uint32_t d;
  asm("mul.rn.bf16x2 %0, %1, %2;" : "=r"(d) : "r"(a), "r"(b));
  return d;
}
__device__ __forceinline__ uint32_t badd(uint32_t a, uint32_t b) {
  uint32_t d;
  asm("add.rn.bf16x2 %0, %1, %2;" : "=r"(d) : "r"(a), "r"(b));
  return d;
}
__device__ __forceinline__ uint32_t bfma(uint32_t a, uint32_t b, uint32_t c) {
  uint32_t d;
  asm("fma.rn.bf16x2 %0, %1, %2, %3;" : "=r"(d) : "r"(a), "r"(b), "r"(c));
  return d;
}
__device__ __forceinline__ float bf_lo(uint32_t x) { return __uint_as_float(x << 16); }
__device__ __forceinline__ float bf_hi(uint32_t x) { return __uint_as_float(x & 0xFFFF0000u); }
__device__ __forceinline__ float ex2(float x) {
  float y;
  asm("ex2.approx.ftz.f32 %0, %1;" : "=f"(y) : "f"(x));
  return y;
}
__device__ __forceinline__ float rcp(float x) {
  float y;
  asm("rcp.approx.ftz.f32 %0, %1;" : "=f"(y) : "f"(x));
  return y;
}
__device__ __forceinline__ void mma16816(float* d, uint32_t a0, uint32_t a1, uint32_t a2, uint32_t a3, uint32_t b0, uint32_t b1) {
  asm volatile("mma.sync.aligned.m16n8k16.row.col.f32.bf16.bf16.f32 {%0, %1, %2, %3}, {%4, %5, %6, %7}, {%8, %9}, {%0, %1, %2, %3};"
               : "+f"(d[0]), "+f"(d[1]), "+f"(d[2]), "+f"(d[3])
               : "r"(a0), "r"(a1), "r"(a2), "r"(a3), "r"(b0), "r"(b1));
}
__device__ __forceinline__ void mma1688(float* d, uint32_t a0, uint32_t a1, uint32_t b0) {
  asm volatile("mma.sync.aligned.m16n8k8.row.col.f32.bf16.bf16.f32 {%0, %1, %2, %3}, {%4, %5}, {%6}, {%0, %1, %2, %3};"
               : "+f"(d[0]), "+f"(d[1]), "+f"(d[2]), "+f"(d[3])
               : "r"(a0), "r"(a1), "r"(b0));
}

template <int N> struct WgRS;
template <int N> struct WgSST;
template <> struct WgRS<32> {
  template <uint32_t HB>
  static __device__ __forceinline__ void mma(float* d, const uint32_t* a, uint32_t db) {
    asm volatile("{\n.reg .pred p;\n.reg .b64 db;\nsetp.ne.b32 p, %22, 0;\n"
      "mov.b64 db, {%20, %21};\n"
      "wgmma.mma_async.sync.aligned.m64n32k16.f32.bf16.bf16 {"
      "%0, %1, %2, %3, %4, %5, %6, %7, %8, %9, %10, %11, %12, %13, %14, %15"
      "}, {%16, %17, %18, %19}, db, p, 1, 1, 1;\n}\n"
      : "+f"(d[0]), "+f"(d[1]), "+f"(d[2]), "+f"(d[3]), "+f"(d[4]), "+f"(d[5]), "+f"(d[6]), "+f"(d[7]),
        "+f"(d[8]), "+f"(d[9]), "+f"(d[10]), "+f"(d[11]), "+f"(d[12]), "+f"(d[13]), "+f"(d[14]), "+f"(d[15])
      : "r"(a[0]), "r"(a[1]), "r"(a[2]), "r"(a[3]), "r"(db), "n"(HB), "n"(1));
  }
  template <uint32_t HB>
  static __device__ __forceinline__ void set(float* d, const uint32_t* a, uint32_t db) {
    asm volatile("{\n.reg .pred p;\n.reg .b64 db;\nsetp.ne.b32 p, %22, 0;\n"
      "mov.b64 db, {%20, %21};\n"
      "wgmma.mma_async.sync.aligned.m64n32k16.f32.bf16.bf16 {"
      "%0, %1, %2, %3, %4, %5, %6, %7, %8, %9, %10, %11, %12, %13, %14, %15"
      "}, {%16, %17, %18, %19}, db, p, 1, 1, 1;\n}\n"
      : "=f"(d[0]), "=f"(d[1]), "=f"(d[2]), "=f"(d[3]), "=f"(d[4]), "=f"(d[5]), "=f"(d[6]), "=f"(d[7]),
        "=f"(d[8]), "=f"(d[9]), "=f"(d[10]), "=f"(d[11]), "=f"(d[12]), "=f"(d[13]), "=f"(d[14]), "=f"(d[15])
      : "r"(a[0]), "r"(a[1]), "r"(a[2]), "r"(a[3]), "r"(db), "n"(HB), "n"(0));
  }
};
template <> struct WgRS<64> {
  template <uint32_t HB>
  static __device__ __forceinline__ void mma(float* d, const uint32_t* a, uint32_t db) {
    asm volatile("{\n.reg .pred p;\n.reg .b64 db;\nsetp.ne.b32 p, %38, 0;\n"
      "mov.b64 db, {%36, %37};\n"
      "wgmma.mma_async.sync.aligned.m64n64k16.f32.bf16.bf16 {"
      "%0, %1, %2, %3, %4, %5, %6, %7, %8, %9, %10, %11, %12, %13, %14, %15, "
      "%16, %17, %18, %19, %20, %21, %22, %23, %24, %25, %26, %27, %28, %29, %30, %31"
      "}, {%32, %33, %34, %35}, db, p, 1, 1, 1;\n}\n"
      : "+f"(d[0]), "+f"(d[1]), "+f"(d[2]), "+f"(d[3]), "+f"(d[4]), "+f"(d[5]), "+f"(d[6]), "+f"(d[7]),
        "+f"(d[8]), "+f"(d[9]), "+f"(d[10]), "+f"(d[11]), "+f"(d[12]), "+f"(d[13]), "+f"(d[14]), "+f"(d[15]),
        "+f"(d[16]), "+f"(d[17]), "+f"(d[18]), "+f"(d[19]), "+f"(d[20]), "+f"(d[21]), "+f"(d[22]), "+f"(d[23]),
        "+f"(d[24]), "+f"(d[25]), "+f"(d[26]), "+f"(d[27]), "+f"(d[28]), "+f"(d[29]), "+f"(d[30]), "+f"(d[31])
      : "r"(a[0]), "r"(a[1]), "r"(a[2]), "r"(a[3]), "r"(db), "n"(HB), "n"(1));
  }
  template <uint32_t HB>
  static __device__ __forceinline__ void set(float* d, const uint32_t* a, uint32_t db) {
    asm volatile("{\n.reg .pred p;\n.reg .b64 db;\nsetp.ne.b32 p, %38, 0;\n"
      "mov.b64 db, {%36, %37};\n"
      "wgmma.mma_async.sync.aligned.m64n64k16.f32.bf16.bf16 {"
      "%0, %1, %2, %3, %4, %5, %6, %7, %8, %9, %10, %11, %12, %13, %14, %15, "
      "%16, %17, %18, %19, %20, %21, %22, %23, %24, %25, %26, %27, %28, %29, %30, %31"
      "}, {%32, %33, %34, %35}, db, p, 1, 1, 1;\n}\n"
      : "=f"(d[0]), "=f"(d[1]), "=f"(d[2]), "=f"(d[3]), "=f"(d[4]), "=f"(d[5]), "=f"(d[6]), "=f"(d[7]),
        "=f"(d[8]), "=f"(d[9]), "=f"(d[10]), "=f"(d[11]), "=f"(d[12]), "=f"(d[13]), "=f"(d[14]), "=f"(d[15]),
        "=f"(d[16]), "=f"(d[17]), "=f"(d[18]), "=f"(d[19]), "=f"(d[20]), "=f"(d[21]), "=f"(d[22]), "=f"(d[23]),
        "=f"(d[24]), "=f"(d[25]), "=f"(d[26]), "=f"(d[27]), "=f"(d[28]), "=f"(d[29]), "=f"(d[30]), "=f"(d[31])
      : "r"(a[0]), "r"(a[1]), "r"(a[2]), "r"(a[3]), "r"(db), "n"(HB), "n"(0));
  }
};
template <> struct WgSST<48> {
  template <uint32_t HA, uint32_t HB>
  static __device__ __forceinline__ void mma(float* d, uint32_t da, uint32_t db, int sc) {
    asm volatile("{\n.reg .pred p;\n.reg .b64 da, db;\nsetp.ne.b32 p, %28, 0;\n"
      "mov.b64 da, {%24, %25};\nmov.b64 db, {%26, %27};\n"
      "wgmma.mma_async.sync.aligned.m64n48k16.f32.bf16.bf16 {"
      "%0, %1, %2, %3, %4, %5, %6, %7, %8, %9, %10, %11, %12, %13, %14, %15, "
      "%16, %17, %18, %19, %20, %21, %22, %23"
      "}, da, db, p, 1, 1, 0, 1;\n}\n"
      : "+f"(d[0]), "+f"(d[1]), "+f"(d[2]), "+f"(d[3]), "+f"(d[4]), "+f"(d[5]), "+f"(d[6]), "+f"(d[7]),
        "+f"(d[8]), "+f"(d[9]), "+f"(d[10]), "+f"(d[11]), "+f"(d[12]), "+f"(d[13]), "+f"(d[14]), "+f"(d[15]),
        "+f"(d[16]), "+f"(d[17]), "+f"(d[18]), "+f"(d[19]), "+f"(d[20]), "+f"(d[21]), "+f"(d[22]), "+f"(d[23])
      : "r"(da), "n"(HA), "r"(db), "n"(HB), "r"(sc));
  }
};
template <> struct WgSST<80> {
  template <uint32_t HA, uint32_t HB>
  static __device__ __forceinline__ void mma(float* d, uint32_t da, uint32_t db, int sc) {
    asm volatile("{\n.reg .pred p;\n.reg .b64 da, db;\nsetp.ne.b32 p, %44, 0;\n"
      "mov.b64 da, {%40, %41};\nmov.b64 db, {%42, %43};\n"
      "wgmma.mma_async.sync.aligned.m64n80k16.f32.bf16.bf16 {"
      "%0, %1, %2, %3, %4, %5, %6, %7, %8, %9, %10, %11, %12, %13, %14, %15, "
      "%16, %17, %18, %19, %20, %21, %22, %23, %24, %25, %26, %27, %28, %29, %30, %31, "
      "%32, %33, %34, %35, %36, %37, %38, %39"
      "}, da, db, p, 1, 1, 0, 1;\n}\n"
      : "+f"(d[0]), "+f"(d[1]), "+f"(d[2]), "+f"(d[3]), "+f"(d[4]), "+f"(d[5]), "+f"(d[6]), "+f"(d[7]),
        "+f"(d[8]), "+f"(d[9]), "+f"(d[10]), "+f"(d[11]), "+f"(d[12]), "+f"(d[13]), "+f"(d[14]), "+f"(d[15]),
        "+f"(d[16]), "+f"(d[17]), "+f"(d[18]), "+f"(d[19]), "+f"(d[20]), "+f"(d[21]), "+f"(d[22]), "+f"(d[23]),
        "+f"(d[24]), "+f"(d[25]), "+f"(d[26]), "+f"(d[27]), "+f"(d[28]), "+f"(d[29]), "+f"(d[30]), "+f"(d[31]),
        "+f"(d[32]), "+f"(d[33]), "+f"(d[34]), "+f"(d[35]), "+f"(d[36]), "+f"(d[37]), "+f"(d[38]), "+f"(d[39])
      : "r"(da), "n"(HA), "r"(db), "n"(HB), "r"(sc));
  }
};
template <> struct WgSST<192> {
  template <uint32_t HA, uint32_t HB>
  static __device__ __forceinline__ void mma(float* d, uint32_t da, uint32_t db, int sc) {
    asm volatile("{\n.reg .pred p;\n.reg .b64 da, db;\nsetp.ne.b32 p, %100, 0;\n"
      "mov.b64 da, {%96, %97};\nmov.b64 db, {%98, %99};\n"
      "wgmma.mma_async.sync.aligned.m64n192k16.f32.bf16.bf16 {"
      "%0, %1, %2, %3, %4, %5, %6, %7, %8, %9, %10, %11, %12, %13, %14, %15, "
      "%16, %17, %18, %19, %20, %21, %22, %23, %24, %25, %26, %27, %28, %29, %30, %31, "
      "%32, %33, %34, %35, %36, %37, %38, %39, %40, %41, %42, %43, %44, %45, %46, %47, "
      "%48, %49, %50, %51, %52, %53, %54, %55, %56, %57, %58, %59, %60, %61, %62, %63, "
      "%64, %65, %66, %67, %68, %69, %70, %71, %72, %73, %74, %75, %76, %77, %78, %79, "
      "%80, %81, %82, %83, %84, %85, %86, %87, %88, %89, %90, %91, %92, %93, %94, %95"
      "}, da, db, p, 1, 1, 0, 1;\n}\n"
      : "+f"(d[0]), "+f"(d[1]), "+f"(d[2]), "+f"(d[3]), "+f"(d[4]), "+f"(d[5]), "+f"(d[6]), "+f"(d[7]),
        "+f"(d[8]), "+f"(d[9]), "+f"(d[10]), "+f"(d[11]), "+f"(d[12]), "+f"(d[13]), "+f"(d[14]), "+f"(d[15]),
        "+f"(d[16]), "+f"(d[17]), "+f"(d[18]), "+f"(d[19]), "+f"(d[20]), "+f"(d[21]), "+f"(d[22]), "+f"(d[23]),
        "+f"(d[24]), "+f"(d[25]), "+f"(d[26]), "+f"(d[27]), "+f"(d[28]), "+f"(d[29]), "+f"(d[30]), "+f"(d[31]),
        "+f"(d[32]), "+f"(d[33]), "+f"(d[34]), "+f"(d[35]), "+f"(d[36]), "+f"(d[37]), "+f"(d[38]), "+f"(d[39]),
        "+f"(d[40]), "+f"(d[41]), "+f"(d[42]), "+f"(d[43]), "+f"(d[44]), "+f"(d[45]), "+f"(d[46]), "+f"(d[47]),
        "+f"(d[48]), "+f"(d[49]), "+f"(d[50]), "+f"(d[51]), "+f"(d[52]), "+f"(d[53]), "+f"(d[54]), "+f"(d[55]),
        "+f"(d[56]), "+f"(d[57]), "+f"(d[58]), "+f"(d[59]), "+f"(d[60]), "+f"(d[61]), "+f"(d[62]), "+f"(d[63]),
        "+f"(d[64]), "+f"(d[65]), "+f"(d[66]), "+f"(d[67]), "+f"(d[68]), "+f"(d[69]), "+f"(d[70]), "+f"(d[71]),
        "+f"(d[72]), "+f"(d[73]), "+f"(d[74]), "+f"(d[75]), "+f"(d[76]), "+f"(d[77]), "+f"(d[78]), "+f"(d[79]),
        "+f"(d[80]), "+f"(d[81]), "+f"(d[82]), "+f"(d[83]), "+f"(d[84]), "+f"(d[85]), "+f"(d[86]), "+f"(d[87]),
        "+f"(d[88]), "+f"(d[89]), "+f"(d[90]), "+f"(d[91]), "+f"(d[92]), "+f"(d[93]), "+f"(d[94]), "+f"(d[95])
      : "r"(da), "n"(HA), "r"(db), "n"(HB), "r"(sc));
  }
};

struct FftConst {
  uint32_t f[2][4], fi[4][4];
  uint32_t ta[2][2], tb[2][2];
};
__device__ __forceinline__ void cis(int m, float scale, float& c, float& s) {
  const float a = (float)m * (-6.283185307179586f * scale);
  c = __cosf(a);
  s = __sinf(a);
}
__device__ __forceinline__ void fft_tables(uint32_t (&v)[12], int tw) {
  const int row = tw >> 2, ch = tw & 3;
#pragma unroll
  for (int i = 0; i < 4; i++) {
    float c[2], s[2], x[2];
#pragma unroll
    for (int e = 0; e < 2; e++) {
      cis((((32 * (8 * ch + 2 * i + e) + 15) * (4 * row - 63) + 2048) & 4095) - 2048, 1.f / 4096, c[e], s[e]);
      float gc, gs;
      cis((((row & 15) * (8 * (ch & 1) + 2 * i + e) + 8) & 15) - 8, 1.f / 16, gc, gs);
      x[e] = (row >> 4) == (ch >> 1) ? gc : (ch >> 1) ? gs : -gs;
    }
    v[i] = pack2(c[0] * 0.125f, c[1] * 0.125f);
    v[4 + i] = pack2(s[0] * 0.125f, s[1] * 0.125f);
    v[8 + i] = pack2(x[0], x[1]);
  }
#pragma unroll
  for (int i = 0; i < 12; i++) asm volatile("" : "+r"(v[i]));
}
__device__ __forceinline__ void fft_tables_store(const uint32_t (&v)[12], uint32_t sb, int tw) {
  const int row = tw >> 2;
  const uint32_t x = ((tw ^ (row >> 1)) & 3) << 4, a = sb + OFF_FT + (16 * (row >> 3) + (row & 7)) * 64 + x;
  sts128(a, v[0], v[1], v[2], v[3]);
  sts128(a + 512, v[4], v[5], v[6], v[7]);
  sts128(sb + OFF_GT + row * 64 + x, v[8], v[9], v[10], v[11]);
}
__device__ __forceinline__ void fft_twiddles(uint32_t (&v)[2], int tw) {
  float a[2], s[2];
#pragma unroll
  for (int i = 0; i < 2; i++) {
    float c;
    cis((2 * (2 * (tw & 3) + i) - 15) * (4 * (tw >> 2) - 63), 1.f / 4096, c, s[i]);
    a[i] = __fdividef(-s[i], 1.f + c);
  }
  v[0] = pack2(a[0], a[1]);
  v[1] = pack2(s[0], s[1]);
  asm volatile("" : "+r"(v[0]), "+r"(v[1]));
}
__device__ __forceinline__ void fft_matrices(FftConst& k, uint32_t sb, int w, int lane) {
  const uint32_t x = (lane >> 1) & 3;
  const uint2 t0 = lds64(sb + OFF_TT + 256 * w + 8 * lane), t1 = lds64(sb + OFF_TT + 256 * w + 8 * (lane ^ 3));
  k.ta[0][0] = t0.x;
  k.tb[0][0] = t0.y;
  k.ta[1][1] = __byte_perm(t1.x, 0, 0x1032);
  k.tb[1][1] = __byte_perm(t1.y, 0, 0x1032);
#pragma unroll
  for (int j = 0; j < 2; j++) {
    k.ta[1 - j][j] = k.ta[j][j] ^ 0x80008000u;
    k.tb[1 - j][j] = k.tb[j][j] ^ 0x80008000u;
    asm volatile("" : "+r"(k.ta[0][j]), "+r"(k.tb[0][j]), "+r"(k.ta[1][j]), "+r"(k.tb[1][j]));
  }
#pragma unroll
  for (int i = 0; i < 2; i++) {
    ldsm4(k.f[i], sb + OFF_FT + (16 * w + (lane & 15)) * 64 + (((2 * i + (lane >> 4)) ^ x) << 4));
    ldsm4t(k.fi[i], sb + OFF_FT + (32 * i + lane) * 64 + ((w ^ x) << 4));
#pragma unroll
    for (int j = 0; j < 4; j++) {
      k.fi[2 + i][j] = (j & 1) ? k.fi[i][j - 1] ^ 0x80008000u : k.fi[i][j + 1];
      asm volatile("" : "+r"(k.fi[2 + i][j]));
    }
  }
}
__device__ __forceinline__ void rot(uint32_t& x, uint32_t& y, uint32_t a, uint32_t b) {
  x = bfma(a, y, x);
  y = bfma(b, x, y);
  x = bfma(a, y, x);
}
__device__ __forceinline__ void twiddle_fwd(uint32_t (&a)[4][4], float* d, const FftConst& k) {
#pragma unroll
  for (int q = 0; q < 4; q++)
#pragma unroll
    for (int j = 0; j < 2; j++) {
      const float* x = d + 8 * q + 4 * j;
      uint32_t re = pack2(x[0], x[1]), im = pack2(x[2], x[3]);
      rot(re, im, k.ta[0][j], k.tb[0][j]);
      a[q & 2][2 * j + (q & 1)] = re;
      a[(q & 2) + 1][2 * j + (q & 1)] = im;
    }
}
__device__ __forceinline__ void g_step(float* d, const uint32_t (&a)[4][4], uint32_t dre, uint32_t dim) {
  WgRS<32>::set<HI_SW64>(d, a[0], dre);
  WgRS<32>::set<HI_SW64>(d + 16, a[2], dre);
  WgRS<32>::mma<HI_SW64>(d, a[1], dim);
  WgRS<32>::mma<HI_SW64>(d + 16, a[3], dim);
  wg_commit();
}

__device__ __forceinline__ void products(uint32_t (&a)[4][4], const float* H, const float* U, int p) {
#pragma unroll
  for (int j = 0; j < 2; j++)
#pragma unroll
    for (int m = 2 * p; m < 2 * p + 2; m++) {
      float pr[2], pi[2];
#pragma unroll
      for (int x = 0; x < 2; x++)
#pragma unroll
        for (int q = 0; q <= m; q++) {
          const int ih = 16 * (q >> 1) + 2 * (q & 1) + 4 * j + x, iu = 16 * ((m - q) >> 1) + 2 * ((m - q) & 1) + 4 * j + x;
          pr[x] = q ? fmaf(H[ih], U[iu], pr[x]) : H[ih] * U[iu];
          pi[x] = q ? fmaf(H[ih], U[iu + 8], pi[x]) : H[ih] * U[iu + 8];
          pr[x] = fmaf(-H[ih + 8], U[iu + 8], pr[x]);
          pi[x] = fmaf(H[ih + 8], U[iu], pi[x]);
        }
      a[m & 2][2 * j + (m & 1)] = pack2(pr[0], pr[1]);
      a[(m & 2) + 1][2 * j + (m & 1)] = pack2(pi[0], pi[1]);
    }
}

__device__ __forceinline__ void conv_channel(const FftConst& k, uint32_t sb, int c, int wg, int w, int lane) {
  const uint32_t cb = sb + off_ch(c), bars = sb + OFF_BAR;
  const uint32_t du = desc_lo(cb, 1024), dg = desc_lo(sb + OFF_GT, 16), dz = desc_lo(cb + U_BYTES, 16);
  float U[32], H[32];
  uint32_t a[4][4], e[4][4];
  const float dv = __uint_as_float(lds32(sb + OFF_D + 4 * c));
  wg_fence();
  WgRS<64>::set<HI_SW32>(H, k.f[0], du + 256);
  WgRS<64>::mma<HI_SW32>(H, k.f[1], du + 256 + 32);
  wg_commit();
  wg_wait<0>();
  pin<32>(H);
  twiddle_fwd(a, H, k);
  if (ATT_GATE) mbar_wait(bars + 8 * (ATT_GATE == 1 ? B_ATTN : B_ATT2), 0);
  mbar_wait(bars + 8 * (B_U + (c < 3 ? c : 3)), 0);
  TSM(w == 0 && c < 3, 7 + wg);
  wg_fence();
  WgRS<64>::set<HI_SW32>(U, k.f[0], du);
  WgRS<64>::mma<HI_SW32>(U, k.f[1], du + 32);
  wg_commit();
  g_step(H, a, dg, dg + 64);
  wg_wait<1>();
  pin<32>(U);
  twiddle_fwd(e, U, k);
  wg_fence();
  g_step(U, e, dg, dg + 64);
  wg_wait<0>();
  pin<32>(U);
  pin<32>(H);
#pragma unroll
  for (int j = 0; j < 4; j++) H[4 * (j >> 1) + (j & 1)] += dv;
  float V[32];
#pragma unroll
  for (int p = 0; p < 2; p++) {
    products(a, H, U, p);
    wg_fence();
    WgRS<32>::set<HI_SW64>(V + 16 * p, a[2 * p], dg + 64);
    WgRS<32>::mma<HI_SW64>(V + 16 * p, a[2 * p + 1], dg);
    wg_commit();
  }
  const uint32_t za = cb + U_BYTES + (8 * w + (lane & 7)) * 128 + (((lane >> 3) ^ (lane & 7)) << 4);
  const uint32_t ya = cb + (lane >> 4) * 1024 + (8 * w + (lane & 7)) * 32 + ((((lane >> 3) ^ (lane >> 2)) & 1) << 4);
  wg_sync(1 + wg);
#pragma unroll
  for (int p = 0; p < 2; p++) {
    if (p == 0) wg_wait<1>();
    else wg_wait<0>();
    pin<16>(V + 16 * p);
#pragma unroll
    for (int i = 0; i < 4; i++) {
      const int j = i & 1;
      const float* x = V + 16 * p + 4 * j + (i & 2);
      e[p][i] = pack2(x[8], x[9]);
      e[2 + p][i] = pack2(x[0], x[1]);
      rot(e[p][i], e[2 + p][i], k.ta[1][j], k.tb[1][j]);
    }
    stsm4(za ^ (64 * p), e[p]);
    stsm4((za ^ (64 * p)) + 4096, e[2 + p]);
  }
  fence_async_smem();
  wg_sync(1 + wg);
  wg_fence();
  WgRS<64>::set<HI_SW128>(H, k.fi[0], dz);
#pragma unroll
  for (int ks = 1; ks < 4; ks++) WgRS<64>::mma<HI_SW128>(H, k.fi[ks], dz + 128 * ks);
  wg_commit();
  if (WO_GATE == 3 && lane == 0) mbar_arrive(bars + 8 * B_CVD);
  wg_wait<0>();
  pin<32>(H);
  if (WO_GATE == 4 && lane == 0) mbar_arrive(bars + 8 * B_CVD);
  TSIF(w == 0, 88 + c);
#pragma unroll
  for (int j = 0; j < 8; j++)
    a[j >> 2][j & 3] = j < 2 ? pack2(H[4 * j], H[4 * j + 1]) : pack2(H[4 * j] + H[4 * j - 6], H[4 * j + 1] + H[4 * j - 5]);
  stsm4(ya, a[0]);
  stsm4(ya + 2048, a[1]);
  fence_async_smem();
  __syncwarp();
}

__device__ __forceinline__ void prep_slab(uint4* res, const uint2* sw, uint32_t sb, int slab, int w, int lane) {
  const int t = lane & 3, tp = (lane & 7) >> 1, pos = 8 * tp + 2 * (((lane >> 3) + tp) & 3) + (lane & 1);
  const uint32_t base = sb + OFF_KVS + slab * KVS_BYTES + pos * 128;
  uint32_t kk[2][4][4], vv[2][4];
  mbar_wait(sb + OFF_BAR + 8 * (B_KV + slab), 0);
#pragma unroll
  for (int h = 0; h < 2; h++) {
#pragma unroll
    for (int j = 0; j < 4; j++) {
      const uint32_t a = base + 128 * j;
      ldsm4t(kk[h][j], a + (((w + 4 * h) ^ ((a >> 7) & 7)) << 4));
    }
    const uint32_t a = base + KVS_V;
    ldsm4t(vv[h], a + (((w + 4 * h) ^ ((a >> 7) & 7)) << 4));
  }
#pragma unroll
  for (int h = 0; h < 2; h++) {
    uint32_t (&k)[4][4] = kk[h];
    uint32_t (&v)[4] = vv[h];
    const uint32_t w0 = __byte_perm(sw[h].x, 0, 0x1010), w1 = __byte_perm(sw[h].x, 0, 0x3232);
    const uint32_t w2 = __byte_perm(sw[h].y, 0, 0x1010), w3 = __byte_perm(sw[h].y, 0, 0x3232);
#pragma unroll
    for (int m = 0; m < 4; m++)
      v[m] = bmul(badd(badd(badd(bmul(k[0][m], w3), bmul(k[1][m], w2)), bmul(k[2][m], w1)), bmul(k[3][m], w0)), v[m]);
    uint32_t a[4];
#pragma unroll
    for (int m = 0; m < 4; m++) a[m] = (t & 1) ? v[(m + 3) & 3] : v[m];
    res[h] = (t & 2) ? make_uint4(a[2], a[3], a[0], a[1]) : make_uint4(a[0], a[1], a[2], a[3]);
  }
}

__device__ __forceinline__ void prep_gate(const Params& p, uint32_t sb, int b, int w, int lane) {
  uint2 gw[5], x[4][5];
#pragma unroll
  for (int j = 0; j < 5; j++) gw[j] = ldg64(reinterpret_cast<const uint2*>(p.gate_w) + lane + 32 * j);
#pragma unroll
  for (int i = 0; i < 4; i++)
#pragma unroll
    for (int j = 0; j < 5; j++)
      x[i][j] = ldg64(reinterpret_cast<const uint2*>(p.q) + (16 * b + 4 * w + i) * (DIM / 4) + lane + 32 * j);
  float s[4];
#pragma unroll
  for (int i = 0; i < 4; i++) {
    s[i] = 0.f;
#pragma unroll
    for (int j = 0; j < 5; j++) {
      const uint32_t m0 = bmul(x[i][j].x, gw[j].x), m1 = bmul(x[i][j].y, gw[j].y);
      s[i] += (bf_lo(m0) + bf_hi(m0)) + (bf_lo(m1) + bf_hi(m1));
    }
  }
  const bool h = lane & 16, q = lane & 8;
  const float a = (h ? s[2] : s[0]) + __shfl_xor_sync(0xffffffffu, h ? s[0] : s[2], 16);
  const float c = (h ? s[3] : s[1]) + __shfl_xor_sync(0xffffffffu, h ? s[1] : s[3], 16);
  float z = (q ? c : a) + __shfl_xor_sync(0xffffffffu, q ? a : c, 8);
#pragma unroll
  for (int o = 4; o > 0; o >>= 1) z += __shfl_xor_sync(0xffffffffu, z, o);
  z = bf_lo(pack2(z, 0.f));
  z = bf_lo(pack2(__fdividef(1.f, 1.f + __expf(-z)), 0.f));
  if (G_TMA) {
    mbar_wait(sb + OFF_BAR + 8 * B_S3, 0);
    if ((lane & 7) == 0) asm volatile("st.shared.f32 [%0], %1;" ::"r"(sb + OFF_GATE + 64 * (b & 7) + 16 * w + (lane >> 1)), "f"(z) : "memory");
    fence_async_smem();
  } else if ((lane & 7) == 0) {
    g_gate[16 * b + 4 * w + (lane >> 3)] = z;
  }
}

__device__ __forceinline__ uint32_t bmax(uint32_t a, uint32_t b) {
  uint32_t d;
  asm("max.bf16x2 %0, %1, %2;" : "=r"(d) : "r"(a), "r"(b));
  return d;
}
__device__ __forceinline__ void softmax_two(const float (&l)[2][2], uint32_t& p0, uint32_t& p1) {
  constexpr float kScale = 0.22360679774997896f, kLog2e = 1.4426950408889634f;
  const uint32_t r0 = pack2(l[0][0], l[1][0]), r1 = pack2(l[0][1], l[1][1]);
  const uint32_t x0 = pack2(bf_lo(r0) * kScale, bf_hi(r0) * kScale), x1 = pack2(bf_lo(r1) * kScale, bf_hi(r1) * kScale);
  uint32_t m = bmax(x0, x1);
  m = bmax(m, __shfl_xor_sync(0xffffffffu, m, 1));
  m = bmax(m, __shfl_xor_sync(0xffffffffu, m, 2));
  const float m0 = bf_lo(m) * kLog2e, m1 = bf_hi(m) * kLog2e;
  p0 = pack2(ex2(bf_lo(x0) * kLog2e - m0), ex2(bf_lo(x1) * kLog2e - m0));
  p1 = pack2(ex2(bf_hi(x0) * kLog2e - m1), ex2(bf_hi(x1) * kLog2e - m1));
}

__device__ __forceinline__ void halo_read(uint32_t (&kpv)[10], uint32_t (&vpv)[10], uint32_t (&tg)[7], const uint4* hp) {
#pragma unroll
  for (int j = 0; j < 7; j++) {
    uint32_t x0, x1, x2;
    asm volatile("ld.relaxed.gpu.global.v4.u32 {%0, %1, %2, %3}, [%4];"
                 : "=r"(x0), "=r"(x1), "=r"(x2), "=r"(tg[j]) : "l"(hp + 32 * j) : "memory");
    if (j < 4) kpv[3 * j] = x0; else vpv[3 * j - 10] = x0;
    if (j < 3) kpv[3 * j + 1] = x1; else vpv[3 * j - 9] = x1;
    if (j < 3) kpv[3 * j + 2] = x2; else if (j < 6) vpv[3 * j - 8] = x2;
  }
}

template <int ROT>
__device__ __forceinline__ void pack_qkv(const float* acc, uint32_t (&qlo)[10], uint32_t (&qhi)[10], uint32_t (&klo)[10],
                                         uint32_t (&khi)[10], uint32_t (&vlo)[10], uint32_t (&vhi)[10]) {
#pragma unroll
  for (int j = 0; j < 10; j++) {
    const int x = (j + ROT) % 10, tq = x < 8 ? x : 16 + x, tk = x < 8 ? 8 + x : 18 + x, tv = x < 8 ? 16 + x : 20 + x;
    khi[j] = pack2(acc[4 * tk + 2], acc[4 * tk + 3]);
    vhi[j] = movm(pack2(acc[4 * tv + 2], acc[4 * tv + 3]));
    qlo[j] = pack2(acc[4 * tq], acc[4 * tq + 1]);
    qhi[j] = pack2(acc[4 * tq + 2], acc[4 * tq + 3]);
    klo[j] = pack2(acc[4 * tk], acc[4 * tk + 1]);
    vlo[j] = pack2(acc[4 * tv], acc[4 * tv + 1]);
    asm volatile("" : "+r"(khi[j]), "+r"(qlo[j]), "+r"(qhi[j]), "+r"(klo[j]), "+r"(vlo[j]));
  }
}

template <int ROT> __device__ __forceinline__ void halo_send(const float* acc, uint4* ho, uint32_t tag) {
#pragma unroll
  for (int j = 0; j < 7; j++) {
    uint32_t x[3];
#pragma unroll
    for (int e = 0; e < 3; e++) {
      const int i = 3 * j + e, y = (i % 10 + ROT) % 10, tk = y < 8 ? 8 + y : 18 + y, tv = y < 8 ? 16 + y : 20 + y;
      x[e] = i < 10 ? pack2(acc[4 * tk + 2], acc[4 * tk + 3]) : i < 20 ? movm(pack2(acc[4 * tv + 2], acc[4 * tv + 3])) : 0u;
    }
    asm volatile("st.relaxed.gpu.global.v4.u32 [%0], {%1, %2, %3, %4};" ::"l"(ho + 32 * j), "r"(x[0]), "r"(x[1]), "r"(x[2]), "r"(tag) : "memory");
  }
}

__device__ __forceinline__ void attention(float* acc, uint32_t sb, int b, int par, int w, int lane, uint32_t tag, uint32_t zero) {
  const int g = lane >> 2, t = lane & 3;
  uint32_t klo[10], khi[10], vlo[10], vhi[10], qlo[10], qhi[10], kpv[10], vpv[10];
  if (HALO_FIRST && w == 3 && b < NCTA - 8) {
    uint4* ho = g_halo + (b * 2 + par) * 224 + lane;
    if (tail_first(b & 7)) halo_send<8>(acc, ho, tag);
    else halo_send<0>(acc, ho, tag);
    TSIF(par == 0, 76);
    pin<120>(acc);
  }
  if (tail_first(b & 7)) pack_qkv<8>(acc, qlo, qhi, klo, khi, vlo, vhi);
  else pack_qkv<0>(acc, qlo, qhi, klo, khi, vlo, vhi);
  const uint32_t xa = sb + OFF_KVX + (par * 3) * 2560 + lane * 16;
  if (w < 3) {
    sts128(xa + w * 2560, khi[0], khi[1], khi[2], khi[3]);
    sts128(xa + w * 2560 + 512, khi[4], khi[5], khi[6], khi[7]);
    sts128(xa + w * 2560 + 1024, khi[8], khi[9], vhi[0], vhi[1]);
    sts128(xa + w * 2560 + 1536, vhi[2], vhi[3], vhi[4], vhi[5]);
    sts128(xa + w * 2560 + 2048, vhi[6], vhi[7], vhi[8], vhi[9]);
  } else if (!HALO_FIRST && b < NCTA - 8) {
    uint4* ho = g_halo + (b * 2 + par) * 224 + lane;
#pragma unroll
    for (int j = 0; j < 7; j++) {
      const uint32_t x0 = j < 4 ? khi[3 * j] : vhi[3 * j - 10], x1 = j < 3 ? khi[3 * j + 1] : vhi[3 * j - 9];
      const uint32_t x2 = j < 3 ? khi[3 * j + 2] : j < 6 ? vhi[3 * j - 8] : 0u;
      asm volatile("st.relaxed.gpu.global.v4.u32 [%0], {%1, %2, %3, %4};" ::"l"(ho + 32 * j), "r"(x0), "r"(x1), "r"(x2), "r"(tag) : "memory");
    }
  }
  TSIF(par == 0 && w == 1, 64);
  TSIF(par == 0 && w == 3 && !HALO_FIRST, 76);
#pragma unroll
  for (int j = 0; j < 10; j++) vlo[j] = movm(vlo[j]);
  const bool far0 = 2 * t > g, far1 = 2 * t + 1 > g;
  const uint32_t mfar = (far0 ? 0x0000FFFFu : 0u) | (far1 ? 0xFFFF0000u : 0u);
  float slo[4][2], shi[4][2], lg[2][2];
  uint32_t phi[4], plo[4], qml[4], qmh[4];
#pragma unroll
  for (int h = 0; h < 4; h++) {
    const int f = h == 0 ? 0 : h == 1 ? 3 : h == 2 ? 5 : 8, hf = h < 2 ? 2 : 7;
    const bool mine = (h & 1) ? t >= 2 : t < 2;
    qml[h] = mine ? qlo[hf] : 0u;
    qmh[h] = mine ? qhi[hf] : 0u;
    float a[4] = {0.f, 0.f, 0.f, 0.f}, c[4] = {0.f, 0.f, 0.f, 0.f};
    mma16816(a, qlo[f], qhi[f], qlo[f + 1], qhi[f + 1], klo[f], klo[f + 1]);
    mma16816(c, qlo[f], qhi[f], qlo[f + 1], qhi[f + 1], khi[f], khi[f + 1]);
    mma1688(a, qml[h], qmh[h], klo[hf]);
    mma1688(c, qml[h], qmh[h], khi[hf]);
    slo[h][0] = a[0];
    slo[h][1] = a[1];
    shi[h][0] = lg[h & 1][0] = far0 ? a[2] : c[2];
    shi[h][1] = lg[h & 1][1] = far1 ? a[3] : c[3];
    if (!ATT_MERGE && (h & 1)) softmax_two(lg, phi[h - 1], phi[h]);
  }
  TSIF(par == 0 && w == 1, 65);
  if (ATT_GATE == 3 && lane == 0) mbar_arrive(sb + OFF_BAR + 8 * B_ATT2 + (phi[3] & zero));
  wg_sync(1 + par);
  TSIF(par == 0 && w == 1, 66);
  const bool nohist = (w == 0) && (b < 8);
  const uint4* hp = g_halo + ((b - 8) * 2 + par) * 224 + lane;
  uint32_t tg[7];
  if (w > 0) {
    const uint4 v0 = lds128(xa + (w - 1) * 2560), v1 = lds128(xa + (w - 1) * 2560 + 512), v2 = lds128(xa + (w - 1) * 2560 + 1024);
    const uint4 v3 = lds128(xa + (w - 1) * 2560 + 1536), v4 = lds128(xa + (w - 1) * 2560 + 2048);
    kpv[0] = v0.x; kpv[1] = v0.y; kpv[2] = v0.z; kpv[3] = v0.w; kpv[4] = v1.x; kpv[5] = v1.y; kpv[6] = v1.z; kpv[7] = v1.w;
    kpv[8] = v2.x; kpv[9] = v2.y; vpv[0] = v2.z; vpv[1] = v2.w; vpv[2] = v3.x; vpv[3] = v3.y; vpv[4] = v3.z; vpv[5] = v3.w;
    vpv[6] = v4.x; vpv[7] = v4.y; vpv[8] = v4.z; vpv[9] = v4.w;
  } else if (nohist) {
#pragma unroll
    for (int j = 0; j < 10; j++) kpv[j] = vpv[j] = 0u;
  } else {
    TSIF(par == 0, 77);
    halo_read(kpv, vpv, tg, hp);
  }
  if (w == 0 && !nohist) {
    int spins = 0;
    while (true) {
      bool ok = true;
#pragma unroll
      for (int j = 0; j < 7; j++) ok = ok && tg[j] == tag;
      if (__all_sync(0xffffffffu, ok) || ++spins > SPIN_LIMIT) break;
      halo_read(kpv, vpv, tg, hp);
    }
    TSIF(par == 0, 79);
  }
#pragma unroll
  for (int h = 0; h < 4; h++) {
    const int f = h == 0 ? 0 : h == 1 ? 3 : h == 2 ? 5 : 8, hf = h < 2 ? 2 : 7;
    float a[4] = {0.f, 0.f, 0.f, 0.f};
    mma16816(a, qlo[f], qhi[f], qlo[f + 1], qhi[f + 1], kpv[f], kpv[f + 1]);
    mma1688(a, qml[h], qmh[h], kpv[hf]);
    const float ninf = __int_as_float(0xff800000);
    lg[h & 1][0] = far0 ? (nohist ? ninf : a[0]) : slo[h][0];
    lg[h & 1][1] = far1 ? (nohist ? ninf : a[1]) : slo[h][1];
    if (h & 1) {
      softmax_two(lg, plo[h - 1], plo[h]);
      if (ATT_MERGE) {
        const float lh[2][2] = {{shi[h - 1][0], shi[h - 1][1]}, {shi[h][0], shi[h][1]}};
        softmax_two(lh, phi[h - 1], phi[h]);
      }
    }
  }
  TSIF(par == 0 && w <= 1, 67 + w);
  if (ATT_GATE == 2 && lane == 0) mbar_arrive(sb + OFF_BAR + 8 * B_ATT2 + (plo[3] & zero));
  uint32_t ov[20];
#pragma unroll
  for (int hp = 0; hp < 2; hp++) {
    const int hf = hp ? 7 : 2;
    float sh[4] = {0.f, 0.f, 0.f, 0.f}, i0 = 0.f, i1 = 0.f;
#pragma unroll
    for (int e = 0; e < 2; e++) {
      const int h = 2 * hp + e, f = h == 0 ? 0 : h == 1 ? 3 : h == 2 ? 5 : 8;
      const uint32_t a0 = plo[h] & mfar, a2 = plo[h] & ~mfar, a3 = phi[h] & mfar, c1 = phi[h] & ~mfar;
      float sum[4] = {0.f, 0.f, 0.f, 0.f};
      mma1688(sum, plo[h], phi[h], 0x3F803F80u);
      const float r0 = rcp(sum[0]), r1 = rcp(sum[2]);
#pragma unroll
      for (int j = f; j < f + 2; j++) {
        float o[4] = {0.f, 0.f, 0.f, 0.f};
        mma16816(o, a0, 0u, a2, a3, vpv[j], vlo[j]);
        mma1688(o, 0u, c1, vhi[j]);
        ov[2 * j] = pack2(o[0] * r0, o[1] * r0);
        ov[2 * j + 1] = pack2(o[2] * r1, o[3] * r1);
      }
      const bool mine = e ? g >= 4 : g < 4;
      mma16816(sh, a0, 0u, a2, a3, mine ? vpv[hf] : 0u, mine ? vlo[hf] : 0u);
      mma1688(sh, 0u, c1, mine ? vhi[hf] : 0u);
      if (e == 0 || t >= 2) {
        i0 = r0;
        i1 = r1;
      }
    }
    ov[2 * hf] = pack2(sh[0] * i0, sh[1] * i0);
    ov[2 * hf + 1] = pack2(sh[2] * i1, sh[3] * i1);
  }
  if (ATT_GATE == 4 && lane == 0) mbar_arrive(sb + OFF_BAR + 8 * B_ATT2 + (ov[19] & zero));
  TS(32 + 4 * par + w);
  mbar_wait(sb + OFF_BAR + 8 * B_P1, 0);
  const uint32_t oa = sb + OFF_OA + (lane >> 4) * 2048 + (32 * w + 2 * (lane & 15) + par) * 16;
#pragma unroll
  for (int j = 0; j < 5; j++) stsm4(oa + 4096 * j, ov + 4 * j);
  TSIF(par == 0 && w == 0, 120);
  fence_async_smem();
  TSIF(par == 0 && w == 0, 121);
  __syncwarp();
  if (lane == 0) mbar_arrive(sb + OFF_BAR + 8 * B_ATTN);
  TSM(w == 0 || w == 2, 122 + par + (w == 2 ? 3 : 0));
}

struct Maps {
  CUtensorMap x, wm, wt, k, v, y, wo, qm, qt, om, ot, u;
};

__device__ __forceinline__ void load_stage(uint32_t sb, int kb, int b, const Maps& m) {
  const uint32_t st = sb + (kb & 3) * STAGE_BYTES, bar = sb + OFF_BAR + 8 * (B_FULL1 + (kb & 3));
  const int r = b >> 3, hg = b & 7, slab = kb - KV_KB;
  const bool kv = slab >= 0 && slab < 5;
  const uint32_t kbar = sb + OFF_BAR + 8 * (B_KV + slab), dst = sb + OFF_KVS + slab * KVS_BYTES;
  mbar_expect_tx(bar, STAGE_BYTES);
  if (kv) mbar_expect_tx(kbar, KVS_BYTES);
  tma_3d(st, &m.x, 64 * kb, 64 * r, 0, bar);
  if (kv && KV_MIX) tma_3d(dst, &m.k, 0, 32 * (b >> 1) - 3, 2 * slab + (b & 1), kbar);
  tma_3d(st + ST_W, &m.wm, 80 * hg + (tail_first(hg) ? 16 : 0), 64 * kb, 0, bar);
  if (kv && KV_MIX) tma_3d(dst + KVS_V, &m.v, 0, 32 * (b >> 1), 2 * slab + (b & 1), kbar);
  tma_3d(st + ST_WT, &m.wt, 80 * hg + (tail_first(hg) ? 0 : 64), 64 * kb, 0, bar);
  if (kv && !KV_MIX) tma_3d(dst, &m.k, 0, 32 * (b >> 1) - 3, 2 * slab + (b & 1), kbar);
  if (kv && !KV_MIX) tma_3d(dst + KVS_V, &m.v, 0, 32 * (b >> 1), 2 * slab + (b & 1), kbar);
}

__global__ void __launch_bounds__(NTHR, 1) fused_kernel(const __grid_constant__ Maps m, const Params p) {
  extern __shared__ __align__(1024) uint8_t smem[];
  const uint32_t sb = (uint32_t)__cvta_generic_to_shared(smem);
  const uint32_t bars = sb + OFF_BAR;
  const int tid = threadIdx.x, lane = tid & 31;
  int b = blockIdx.x;
  if (BMAP == 1) b = (((b & 63) >> 3) * 2 + (b & 1)) * 8 + (((b < 64 ? 0x6521 : 0x7430) >> (4 * ((b >> 1) & 3))) & 7);
  if (BMAP == 2) b = ((b & 63) >> 2) * 8 + (((b < 64 ? 0x6521 : 0x7430) >> (4 * (b & 3))) & 7);
  if (BMAP == 3) b = (((b & 63) >> 3) * 2 + (b & 1)) * 8 + (((b < 64 ? 0x7430 : 0x6521) >> (4 * ((b >> 1) & 3))) & 7);
  if (BMAP == 4) b = (((b >> 4) * 2 + (b & 1)) * 8) + ((b >> 1) & 7);
  if (BMAP == 5) b = 127 - b;
  const int r = b >> 3, hg = b & 7;

  if (tid == T_ISSUE) {
    TSM(true, 0);
#pragma unroll
    for (int i = 0; i < 4; i++) mbar_init(bars + 8 * (B_FULL1 + i), 1);
#pragma unroll
    for (int i = 0; i < 3; i++) mbar_init(bars + 8 * (B_KV + i), 1);
    fence_async_smem();
#pragma unroll 1
    for (int kb = 0; kb <= PRE2; kb++) load_stage(sb, kb, b, m);
  } else if (tid >= T_PF && tid < T_PF + 12) {
    tm_prefetch(&m.x + (tid - T_PF));
  } else if (tid == T_INIT) {
#pragma unroll
    for (int i = 0; i < 4; i++) mbar_init(bars + 8 * (B_EMPTY1 + i), 8);
#pragma unroll
    for (int i = 0; i < 8; i++) mbar_init(bars + 8 * (B_FULL2 + i), 1);
#pragma unroll
    for (int i = 0; i < 4; i++) mbar_init(bars + 8 * (B_EMPTY2 + i), 8);
#pragma unroll
    for (int i = 0; i < 4; i++) mbar_init(bars + 8 * (B_U + i), 1);
    mbar_init(bars + 8 * B_HA, 4);
    mbar_init(bars + 8 * B_GATE, 4);
    mbar_init(bars + 8 * B_HB, 1);
    mbar_init(bars + 8 * B_KVD, 4);
    mbar_init(bars + 8 * B_QF, 1);
    mbar_init(bars + 8 * B_ATTN, 8);
    mbar_init(bars + 8 * B_ATT2, 8);
    mbar_init(bars + 8 * B_P1, 8);
    mbar_init(bars + 8 * B_C34, 1);
    mbar_init(bars + 8 * B_YRB, 1);
#pragma unroll
    for (int i = 0; i < 5; i++) mbar_init(bars + 8 * (B_YST + i), 4);
#pragma unroll
    for (int i = 0; i < 5; i++) mbar_init(bars + 8 * (B_US + i), U_TMA ? 4 : i == 2 ? 20 : 1);
    mbar_init(bars + 8 * B_YSIG, 1);
    mbar_init(bars + 8 * B_YFULL, 1);
    mbar_init(bars + 8 * B_EPOCH, 1);
    mbar_init(bars + 8 * B_PREP, 4);
    mbar_init(bars + 8 * B_USIG, 1);
    mbar_init(bars + 8 * B_WST, 1);
#pragma unroll
    for (int i = 3; i < 5; i++) mbar_init(bars + 8 * (B_KV + i), 1);
    mbar_init(bars + 8 * B_E3, 8);
    mbar_init(bars + 8 * B_LAST, 1);
    mbar_init(bars + 8 * B_OSIG, 1);
    mbar_init(bars + 8 * B_WOP, 1);
    fence_async_smem();
  }
  const int warp = __shfl_sync(0xffffffffu, tid >> 5, 0), wg = warp >> 2, w = warp & 3;
  __syncthreads();

  if (wg == 3) {
    asm volatile("setmaxnreg.dec.sync.aligned.u32 56;");
    if (w == 0) {
      if (lane == 0) {
#pragma unroll 1
        for (int kb = 1 + PRE2; kb < 10; kb++) {
          if (kb >= 4) mbar_wait(bars + 8 * (kb == 7 ? B_E3 : B_EMPTY1 + (kb & 3)), (kb >> 3) & 1);
          TSIF(kb >= 4, 44 + kb);
          load_stage(sb, kb, b, m);
          TSIF(kb == 3, 60);
          if (kb == TRIG_KB) mbar_arrive(bars + 8 * B_LAST);
        }
        mbar_wait(bars + 8 * B_WOP, 0);
        mbar_wait(bars + 8 * WL_TRIG, 0);
        mbar_wait(bars + 8 * B_EPOCH, 0);
        flag_wait(g_cnt + C_W + 32 * hg, (lds32(sb + OFF_EPOCH) + 1) * 16);
        TS(30);
#pragma unroll 1
        for (int j = 0; j < 8; j++) {
          if (j >= 6) mbar_wait(bars + 8 * (B_EMPTY2 + j - 6), 0);
          if (j == 4) mbar_wait(bars + 8 * B_ATTN, 0);
          TSIF(j >= 6, 100 + j);
          if (RF_GATE && j == 6) mbar_wait(bars + 8 * B_YSIG, 0);
          mbar_expect_tx(bars + 8 * (B_FULL2 + j), j == 0 ? WO_BYTES : j == 5 ? O_BYTES + WO_BYTES + 512 : O_BYTES + WO_BYTES);
          bulk_load(sb + off_w(j), g_WO + (hg * 8 + step_src(hg, j)) * 800, WO_BYTES, bars + 8 * (B_FULL2 + j));
        }
        mbar_wait(bars + 8 * (B_EMPTY2 + Q_SLOT), 0);
        mbar_expect_tx(bars + 8 * B_QF, O_BYTES);
        tma_2d(sb + OFF_QS, &m.qm, 80 * hg, 128 * r, bars + 8 * B_QF);
        if (!QBOX) tma_2d(sb + OFF_QT, &m.qt, 80 * hg + 64, 128 * r, bars + 8 * B_QF);
      }
    } else if (w == 1) {
      unsigned epoch = 0;
      if (lane == 0) {
        epoch = atomicAdd(g_cnt + C_LAUNCH, 1u) / NCTA;
        asm volatile("st.shared.u32 [%0], %1;" ::"r"(sb + OFF_EPOCH), "r"(epoch) : "memory");
        mbar_arrive(bars + 8 * B_EPOCH);
        mbar_wait(bars + 8 * B_KVD, 0);
        mbar_expect_tx(bars + 8 * B_HB, 5 * 4096);
#pragma unroll 1
        for (int c = 0; c < 5; c++) {
          if (c == 3) mbar_wait(bars + 8 * B_S3, 0);
          bulk_load(sb + off_ch(c) + U_BYTES, p.ssm_k + (5 * b + c) * SEQ, 4096, bars + 8 * B_HB);
        }
#pragma unroll
        for (int c = 0; c < 4; c++) mbar_expect_tx(bars + 8 * (B_U + c), c < 3 ? U_BYTES : 2 * U_BYTES);
        const uint4* usrc = g_U + 5 * b * U_PITCH;
        mbar_wait(bars + 8 * B_USIG, 0);
        flag_wait(g_cnt + C_PREP + 32 * (b & 15), (epoch + 1) * NCTA);
        TS(23);
#pragma unroll
        for (int c = 0; c < 5; c++) {
          if (c == 3 && U_TRIM) mbar_wait(bars + 8 * (B_U + 2), 0);
          bulk_load(sb + off_ch(c), usrc + c * U_PITCH, U_BYTES, bars + 8 * (B_U + (c < 3 ? c : 3)));
          TSIF(c == 0 || c == 4, 116 + (c >> 2));
        }
      }
      epoch = __shfl_sync(0xffffffffu, epoch, 0);
      if (lane < 8) {
        const int src = (b & ~7) | step_src(hg, lane);
        mbar_wait(bars + 8 * OP_TRIG, 0);
        TS(20);
        bool seen = false;
#pragma unroll 1
        for (int spins = 0; spins < SPIN_LIMIT; spins++) {
          const bool now = !seen && (int)(flag_read(g_cnt + C_O + 32 * src) - (epoch + 1)) >= 0;
          if (now && lane >= 1 && lane < 4) bulk_load(sb + off_o(lane), g_O + src * 1280, O_BYTES, bars + 8 * (B_FULL2 + lane));
          seen = seen || now;
          if (__all_sync(0xff, seen)) break;
        }
        TS(21);
        if (lane == 5) bulk_load(sb + OFF_GATE, g_gate + 128 * r, 512, bars + 8 * (B_FULL2 + 5));
#pragma unroll 1
        for (int j = 4; j < 8; j++) {
          if (lane == j) {
            mbar_wait(bars + 8 * (j < 6 ? B_C34 : B_EMPTY2 + j - 6), 0);
            if (RF_GATE && j == 6) mbar_wait(bars + 8 * B_YSIG, 0);
            bulk_load(sb + off_o(j), g_O + src * 1280, O_BYTES, bars + 8 * (B_FULL2 + j));
          }
          __syncwarp(0xff);
        }
        TS(22);
      }
    } else if (w == 2) {
      mbar_wait(bars + 8 * B_PREP, 0);
      flag_signal(g_cnt + C_PREP, 16, lane);
      TS(25);
      if (lane == 0) mbar_arrive(bars + 8 * B_USIG);
      mbar_wait(bars + 8 * B_GATE, 0);
      if (G_TMA) {
        if (lane == 0) {
          asm volatile("cp.async.bulk.global.shared::cta.bulk_group [%0], [%1], 64;\ncp.async.bulk.commit_group;\n"
                       "cp.async.bulk.wait_group.read 0;" ::"l"(g_gate + 16 * b), "r"(sb + OFF_GATE + 64 * hg) : "memory");
          bulk_load(sb + OFF_GATE + 64 * hg, g_gate + 16 * b, 64, bars + 8 * B_ORB);
        }
      } else if (((NOMB & 1) || O_RB) && lane == 0) {
        asm volatile("fence.release.gpu;" ::: "memory");
      }
      mbar_wait(bars + 8 * B_ATTN, 0);
      if (lane == 0) {
        if (O_DEFER) mbar_wait(bars + 8 * (B_U + 3), 0);
        asm volatile("cp.async.bulk.global.shared::cta.bulk_group [%0], [%1], 20480;\ncp.async.bulk.commit_group;"
                     ::"l"(g_O + b * 1280), "r"(sb + OFF_OA) : "memory");
        if (O_RB == 2) {
          asm volatile("cp.async.bulk.wait_group.read 0;" ::: "memory");
          mbar_expect_tx(bars + 8 * B_ORB, O_BYTES + 64 * G_TMA);
          bulk_load(sb + OFF_OA, g_O + b * 1280, O_BYTES, bars + 8 * B_ORB);
          mbar_wait(bars + 8 * B_ORB, 0);
          flag_bump(g_cnt + C_O + 32 * b);
        } else if (O_RB) asm volatile("cp.async.bulk.wait_group.read 0;" ::: "memory");
        else asm volatile("cp.async.bulk.wait_group 0;\nfence.proxy.async.global;" ::: "memory");
      }
      TS(74);
      if (O_RB == 2) {
      } else if (O_RB) {
        __syncwarp();
        unsigned v[5];
#pragma unroll
        for (int c = 0; c < 5; c++) v[c] = flag_read(reinterpret_cast<const unsigned*>(g_O + b * 1280 + 256 * c + 8 * lane + 7));
        const unsigned dep = __reduce_or_sync(0xffffffffu, (v[0] ^ v[1] ^ v[2] ^ v[3] ^ v[4]) & p.zero);
        if (lane == 0) flag_bump(g_cnt + C_O + 32 * b + dep);
      } else if (!(NOMB & 1)) flag_signal(g_cnt + C_O + 32 * b, 1, lane);
      else if (lane == 0) flag_bump(g_cnt + C_O + 32 * b);
      TS(26);
      if (lane == 0) mbar_arrive(bars + 8 * B_OSIG);

    } else {
      if (lane == 0) {
        uint4* dst = g_WO + (hg * 8 + (r >> 1)) * 800 + (r & 1) * 80;
        if (WPF) {
          mbar_wait(bars + 8 * WPF, 0);
          if (WPF_LIN)
            asm volatile("cp.async.bulk.prefetch.L2.global [%0], 6400;" ::"l"(p.wo + b * 3200) : "memory");
          else
            asm volatile("cp.async.bulk.prefetch.tensor.3d.L2.global [%0, {%1, %2, %3}];" ::"l"(&m.wo), "r"(0), "r"(40 * r), "r"(5 * hg) : "memory");
        }
        mbar_wait(bars + 8 * B_P1, 0);
        mbar_wait(bars + 8 * WB_TRIG, 0);
        mbar_expect_tx(bars + 8 * B_WST, WO_BYTES / 2);
        tma_3d(sb + OFF_WS, &m.wo, 0, 40 * r, 5 * hg, bars + 8 * B_WST);
        mbar_wait(bars + 8 * B_WST, 0);
        mbar_wait(bars + 8 * WO_TRIG, 0);
#pragma unroll 1
        for (int n = 0; n < 5; n++)
          asm volatile("cp.async.bulk.global.shared::cta.bulk_group [%0], [%1], 1280;" ::"l"(dst + 160 * n), "r"(sb + OFF_WS + 1280 * n) : "memory");
        if (W_RB) {
          asm volatile("cp.async.bulk.commit_group;\ncp.async.bulk.wait_group.read 0;" ::: "memory");
          mbar_expect_tx(bars + 8 * B_WST, WO_BYTES / 2);
#pragma unroll 1
          for (int n = 0; n < 5; n++) bulk_load(sb + OFF_WS + 1280 * n, dst + 160 * n, 1280, bars + 8 * B_WST);
          mbar_wait(bars + 8 * B_WST, 1);
        } else {
          asm volatile("cp.async.bulk.commit_group;\ncp.async.bulk.wait_group 0;\nfence.proxy.async.global;" ::: "memory");
          if (!(NOMB & 4)) asm volatile("fence.release.gpu;" ::: "memory");
        }
        flag_bump(g_cnt + C_W + 32 * hg);
        mbar_arrive(bars + 8 * B_WOP);
        TS(71);
        mbar_expect_tx(bars + 8 * B_C34, 3 * U_BYTES);
        mbar_expect_tx(bars + 8 * B_YRB, 2 * U_BYTES);
#pragma unroll 1
        for (int c = 0; c < 5; c++) {
          mbar_wait(bars + 8 * (B_YST + c), 0);
          asm volatile("cp.async.bulk.global.shared::cta.bulk_group [%0], [%1], 4096;\ncp.async.bulk.commit_group;\n"
                       "cp.async.bulk.wait_group.read 0;" ::"l"(g_Y + (5 * b + c) * Y_PITCH), "r"(sb + off_ch(c)) : "memory");
          bulk_load(sb + off_ch(c), g_Y + (5 * b + c) * Y_PITCH, U_BYTES, bars + 8 * (c < 3 ? B_C34 : B_YRB));
        }
        TS(75);
        mbar_wait(bars + 8 * B_C34, 0);
        mbar_wait(bars + 8 * B_YRB, 0);
        flag_bump(g_cnt + C_Y + 32 * (b >> 4));
        TS(27);
        mbar_arrive(bars + 8 * B_YSIG);
        mbar_expect_tx(bars + 8 * B_YFULL, 20480);
        flag_wait(g_cnt + C_Y + 32 * hg, (lds32(sb + OFF_EPOCH) + 1) * 16);
        TS(24);
        tma_2d(sb + OFF_YT, &m.y, 128 * r, 80 * hg, bars + 8 * B_YFULL);
        tma_2d(sb + OFF_YT + 10240, &m.y, 128 * r + 64, 80 * hg, bars + 8 * B_YFULL);
      }
    }
  } else {
    asm volatile("setmaxnreg.inc.sync.aligned.u32 152;");
    if (wg < 2) {
      float acc[120];
#pragma unroll
      for (int i = 0; i < 120; i++) acc[i] = 0.f;
      const uint32_t da = desc_lo(sb + wg * 8192, 16), db = desc_lo(sb + ST_W, 8192), dc = desc_lo(sb + ST_WT, 2048);
      if (PW1) pin<120>(acc);
      if (PW1 == 2) mbar_wait(bars + 8 * B_FULL1, 0);
#pragma unroll 1
      for (int kb = 0; kb < 10; kb++) {
        mbar_wait(bars + 8 * (B_FULL1 + (kb & 3)), (kb >> 2) & 1);
        const uint32_t so = (kb & 3) * (STAGE_BYTES >> 4);
        wg_fence();
#pragma unroll
        for (int k = 0; k < 4; k++) {
          WgSST<192>::mma<HI_SW128, HI_SW128>(acc, da + so + 2 * k, db + so + 128 * k, 1);
          WgSST<48>::mma<HI_SW128, HI_SW32>(acc + 96, da + so + 2 * k, dc + so + 32 * k, 1);
        }
        wg_commit();
        wg_wait<1>();
        if (kb > 0 && lane == 0) mbar_arrive(bars + 8 * (kb == 4 ? B_E3 : B_EMPTY1 + ((kb - 1) & 3)));
      }
      mbar_wait(bars + 8 * B_EPOCH, 0);
      const uint32_t tag = lds32(sb + OFF_EPOCH) + 1;
      mbar_wait(bars + 8 * B_S3, 0);
      wg_wait<0>();
      pin<120>(acc);
      if (lane == 0) mbar_arrive(bars + 8 * B_P1);
      TSM(w == 0, 3 + wg);
      attention(acc, sb, b, wg, w, lane, tag, p.zero);
    } else {
      const int tw = tid & 127, chl = 64 * (b & 1) + 8 * w + (lane >> 2);
      uint4* up = g_U + chl * U_PITCH + ((4 * (b >> 1) + (lane & 3)) ^ ((b >> 2) & 1));
      uint2 sw[10];
      uint32_t dv = 0;
      if (lane < 5) dv = __ldg(reinterpret_cast<const unsigned short*>(p.ssm_D) + 5 * b + lane);
#pragma unroll
      for (int i = 0; i < 10; i++) sw[i] = ldg64(reinterpret_cast<const uint2*>(p.shift_k) + chl + 128 * (i >> 1) + 32 * (i & 1));
      uint32_t tab[12];
      uint32_t tt[2];
      fft_tables(tab, tw);
      fft_twiddles(tt, tw);
      uint4 res[10];
#pragma unroll
      for (int i = 0; i < 10; i++) res[i] = make_uint4(0, 0, 0, 0);
#pragma unroll 1
      for (int slab = 0; slab < 5; slab++) {
#pragma unroll
        for (int i = 0; i < 8; i++) res[i] = res[i + 2];
        prep_slab(res + 8, sw, sb, slab, w, lane);
        TSIF(w == 0, 99 + 4 * slab);
#pragma unroll
        for (int i = 0; i < 8; i++) sw[i] = sw[i + 2];
      }
      TSIF(w == 0, 28);
      __syncwarp();
      if (lane == 0) mbar_arrive(bars + 8 * B_KVD + ((res[8].x ^ res[9].x) & p.zero));
      mbar_wait(bars + 8 * B_KVD, 0);
      fft_tables_store(tab, sb, tw);
      mbar_wait(bars + 8 * B_LAST, 0);
#pragma unroll
      for (int i = 0; i < 10; i++) up[(128 * (i >> 1) + 32 * (i & 1)) * U_PITCH] = res[i];
      __syncwarp();
      if (lane == 0) mbar_arrive(bars + 8 * B_PREP);
      TSIF(w == 0 && !U_TMA, 5);
      mbar_wait(bars + 8 * (G_AFTER ? B_USIG : B_LAST), 0);
      prep_gate(p, sb, b, w, lane);
      __syncwarp();
      if (lane == 0) mbar_arrive(bars + 8 * B_GATE);
      TSIF(w == 0, 72);
      mbar_wait(bars + 8 * B_HB, 0);
      TSIF(w == 0, 2);
      const uint32_t ha = sb + U_BYTES + ((tw >> 3) * 16 + 8 + (tw & 7)) * 16;
      uint4 hv[5];
#pragma unroll
      for (int c = 0; c < 5; c++) hv[c] = lds128(ha + off_ch(c));
      __syncwarp();
#pragma unroll
      for (int c = 0; c < 5; c++) sts128((ha ^ 16) + off_ch(c), hv[c].x, hv[c].y, hv[c].z, hv[c].w);
      asm volatile("st.shared.v2.u32 [%0], {%1, %2};" ::"r"(sb + OFF_TT + 8 * tw), "r"(tt[0]), "r"(tt[1]) : "memory");
      if (tw < 5) asm volatile("st.shared.f32 [%0], %1;" ::"r"(sb + OFF_D + 4 * tw), "f"(bf_lo(dv) * 0.125f) : "memory");
      fence_async_smem();
      __syncwarp();
      if (lane == 0) mbar_arrive(bars + 8 * B_HA);
      TSIF(w == 0, 6);
    }

    FftConst fc;
    TSM(w == 0 && wg == 0, 104);
    mbar_wait(bars + 8 * B_HA, 0);
    fft_matrices(fc, sb, w, lane);
    TSM(w == 0 && wg == 0, 105);
    TSM(w == 0 && wg == 2, 124);
#pragma unroll 1
    for (uint32_t tasks = wg == 0 ? TASK0 : wg == 1 ? TASK1 : TASK2; tasks; tasks >>= 4) {
      const int c = (tasks & 7) - 1;
      conv_channel(fc, sb, c, wg, w, lane);
      if (lane == 0) mbar_arrive(bars + 8 * (B_YST + c));
      TSM(w == 0, 10 + c);
    }

    if (wg < 2) {
      const int g = lane >> 2;
      float acc[40];
#pragma unroll
      for (int i = 0; i < 40; i++) acc[i] = 0.f;
      const uint32_t da = desc_lo(sb + wg * 1024, 2048), db = desc_lo(sb, 2560);
      mbar_wait(bars + 8 * (O_RB == 2 ? B_ORB : B_ATTN), 0);
      if (PW2) mbar_wait(bars + 8 * B_FULL2, 0);
      mbar_wait(bars + 8 * B_CVD, 0);
      TSM(w == 0, 15 + wg);
#pragma unroll 1
      for (int j = 0; j < 8; j++) {
        mbar_wait(bars + 8 * (B_FULL2 + j), 0);
        TSM(w == 0 && wg == 0, 44 + (j < 4 ? j : j + 6));
        const uint32_t oa = da + (off_o(j) >> 4), ob = db + (off_w(j) >> 4);
        wg_fence();
#pragma unroll
        for (int k = 0; k < 5; k++) WgSST<80>::mma<HI_NONE, HI_SW32>(acc, oa + 256 * k, ob + 32 * k, 1);
        wg_commit();
        wg_wait<1>();
        if (j >= 1 && j <= Q_SLOT + 1 && lane == 0) mbar_arrive(bars + 8 * (B_EMPTY2 + j - 1));
      }
      TSIF(w == 0 && wg == 0, 113);
      const int tr = 64 * wg + 16 * w + (lane & 15);
      const uint32_t fm = sb + OFF_QS + tr * 128, fx = (lane >> 4) ^ (tr & 7), fq = sb + OFF_QS + tr * 160 + (lane >> 4) * 16;
      const uint32_t ft = sb + OFF_QT + tr * 32 + (((lane >> 4) ^ (tr >> 2)) & 1) * 16;
      const float g0 = __uint_as_float(lds32(sb + OFF_GATE + (64 * wg + 16 * w + g) * 4));
      const float g1 = __uint_as_float(lds32(sb + OFF_GATE + (64 * wg + 16 * w + 8 + g) * 4));
      const uint32_t ga = pack2(g0, g0), gb = pack2(g1, g1);
      const uint32_t na = pack2(1.f - g0, 1.f - g0), nb = pack2(1.f - g1, 1.f - g1);

      uint32_t qf[20];
      mbar_wait(bars + 8 * B_QF, 0);
      TSM(w == 0 && wg == 0, 99);
#pragma unroll
      for (int j = 0; j < 5; j++) ldsm4(qf + 4 * j, QBOX ? fq + 32 * j : j < 4 ? fm + ((fx ^ (2 * j)) << 4) : ft);
      if (FUSE_MIX) {
#pragma unroll
        for (int i = 0; i < 20; i++) {
          qf[i] = bmul((i & 1) ? gb : ga, qf[i]);
          asm volatile("" : "+r"(qf[i]));
        }
      }
      wg_wait<0>();
      pin<40>(acc);
      TSM(w == 0, 17 + wg);
      uint32_t pb[20];
#pragma unroll
      for (int j = 0; j < 10; j++) {
        pb[2 * j] = bmul(na, pack2(acc[4 * j], acc[4 * j + 1]));
        pb[2 * j + 1] = bmul(nb, pack2(acc[4 * j + 2], acc[4 * j + 3]));
        asm volatile("" : "+r"(pb[2 * j]), "+r"(pb[2 * j + 1]));
      }
      const uint32_t ya = sb + OFF_YT + wg * 10240 + ((lane >> 4) * 8 + (lane & 7)) * 128 +
                          (((2 * w + (((lane >> 3) & 1) ^ wg)) ^ (lane & 7)) << 4);
      mbar_wait(bars + 8 * B_YFULL, 0);
      TSM(w == 0 && wg == 0, 19);
#pragma unroll
      for (int j = 0; j < 5; j++) {
        uint32_t y[4];
        ldsm4t(y, ya + 2048 * j);
#pragma unroll
        for (int i = 0; i < 4; i++)
          qf[4 * j + i] = FUSE_MIX ? bfma(qf[4 * j + i], y[i], pb[4 * j + i]) : badd(bmul((i & 1) ? gb : ga, bmul(qf[4 * j + i], y[i])), pb[4 * j + i]);
      }
#pragma unroll
      for (int j = 0; j < 5; j++) stsm4(QBOX ? fq + 32 * j : j < 4 ? fm + ((fx ^ (2 * j)) << 4) : ft, qf + 4 * j);
      fence_async_smem();
      __syncwarp();
      if (lane == 0) {
        const int row = 64 * wg + 16 * w;
        asm volatile("cp.async.bulk.tensor.2d.global.shared::cta.bulk_group [%0, {%2, %3}], [%1];"
                     ::"l"(&m.om), "r"(sb + OFF_QS + row * (QBOX ? 160 : 128)), "r"(80 * hg), "r"(128 * r + row) : "memory");
        if (!QBOX) asm volatile("cp.async.bulk.tensor.2d.global.shared::cta.bulk_group [%0, {%2, %3}], [%1];"
                     ::"l"(&m.ot), "r"(sb + OFF_QT + row * 32), "r"(80 * hg + 64), "r"(128 * r + row) : "memory");
        asm volatile("cp.async.bulk.commit_group;\ncp.async.bulk.wait_group.read 0;" ::: "memory");
      }
      TSM(w == 0 || w == 3, 40 + 2 * wg + (w & 1));
      if (ENDBAR) asm volatile("bar.sync 15, 256;" ::: "memory");
    }
  }
}

typedef CUresult (*EncodeFn)(CUtensorMap*, CUtensorMapDataType, cuuint32_t, void*, const cuuint64_t*, const cuuint64_t*,
                             const cuuint32_t*, const cuuint32_t*, CUtensorMapInterleave, CUtensorMapSwizzle,
                             CUtensorMapL2promotion, CUtensorMapFloatOOBfill);

void encode(EncodeFn fn, CUtensorMap* tm, const void* base, int rank, const cuuint64_t* dims, const cuuint64_t* strides,
            const cuuint32_t* box, CUtensorMapSwizzle swz) {
  const cuuint32_t ones[3] = {1, 1, 1};
  fn(tm, CU_TENSOR_MAP_DATA_TYPE_BFLOAT16, rank, const_cast<void*>(base), dims, strides, box, ones,
     CU_TENSOR_MAP_INTERLEAVE_NONE, swz, CU_TENSOR_MAP_L2_PROMOTION_L2_128B, CU_TENSOR_MAP_FLOAT_OOB_FILL_NONE);
}

}

extern "C" void kernel_launch(void* const* d_in, const int* in_sizes, int n_in, void* d_out, int out_size) {
  (void)in_sizes; (void)n_in; (void)out_size;
  Params p;
  p.q = (const __nv_bfloat16*)d_in[0];
  p.k = (const __nv_bfloat16*)d_in[1];
  p.v = (const __nv_bfloat16*)d_in[2];
  p.shift_k = (const __nv_bfloat16*)d_in[3];
  p.ssm_k = (const __nv_bfloat16*)d_in[4];
  p.ssm_D = (const __nv_bfloat16*)d_in[5];
  p.wqkv = (const __nv_bfloat16*)d_in[7];
  p.wo = (const __nv_bfloat16*)d_in[8];
  p.gate_w = (const __nv_bfloat16*)d_in[9];
  p.out = (__nv_bfloat16*)d_out;
  p.zero = 0;

  static EncodeFn fn = nullptr;
  static void *yaddr = nullptr, *uaddr = nullptr;
  if (!fn) {
    cudaDriverEntryPointQueryResult qr;
    void* f = nullptr;
    cudaGetDriverEntryPoint("cuTensorMapEncodeTiled", &f, cudaEnableDefault, &qr);
    fn = (EncodeFn)f;
    cudaGetSymbolAddress(&yaddr, g_Y);
    cudaGetSymbolAddress(&uaddr, g_U);
    cudaFuncSetAttribute(fused_kernel, cudaFuncAttributeMaxDynamicSharedMemorySize, SMEM_BYTES);
  }
  Maps m;
  {
    const cuuint64_t dims[3] = {640, 1024, 2}, st[2] = {2560, 1280};
    const cuuint32_t box[3] = {64, 64, 2};
    encode(fn, &m.x, p.q, 3, dims, st, box, CU_TENSOR_MAP_SWIZZLE_128B);
  }
  {
    const cuuint64_t dims[3] = {640, 640, 3}, st[2] = {3840, 1280};
    const cuuint32_t box[3] = {64, 64, 3}, boxt[3] = {16, 64, 3};
    encode(fn, &m.wm, p.wqkv, 3, dims, st, box, CU_TENSOR_MAP_SWIZZLE_128B);
    encode(fn, &m.wt, p.wqkv, 3, dims, st, boxt, CU_TENSOR_MAP_SWIZZLE_32B);
  }
  {
    const cuuint64_t dims[3] = {64, 2048, 10}, st[2] = {1280, 128};
    const cuuint32_t boxk[3] = {64, 35, 1}, boxv[3] = {64, 32, 1};
    encode(fn, &m.k, p.k, 3, dims, st, boxk, CU_TENSOR_MAP_SWIZZLE_128B);
    encode(fn, &m.v, p.v, 3, dims, st, boxv, CU_TENSOR_MAP_SWIZZLE_128B);
  }
  {
    const cuuint64_t dims[3] = {16, 640, 40}, st[2] = {1280, 32};
    const cuuint32_t box[3] = {16, 40, 5};
    encode(fn, &m.wo, p.wo, 3, dims, st, box, CU_TENSOR_MAP_SWIZZLE_32B);
  }
  {
    const cuuint64_t dims[2] = {2048, 640}, st[1] = {Y_PITCH * 16};
    const cuuint32_t box[2] = {64, 80};
    encode(fn, &m.y, yaddr, 2, dims, st, box, CU_TENSOR_MAP_SWIZZLE_128B);
    const cuuint64_t stu[1] = {U_PITCH * 16};
    const cuuint32_t boxu[2] = {32, 64};
    encode(fn, &m.u, uaddr, 2, dims, stu, boxu, CU_TENSOR_MAP_SWIZZLE_NONE);
  }
  {
    const cuuint64_t dims[2] = {640, 2048}, st[1] = {1280};
    const cuuint32_t bqm[2] = {QBOX ? 80 : 64, 128}, bqt[2] = {16, 128}, bom[2] = {QBOX ? 80 : 64, 16}, bot[2] = {16, 16};
    encode(fn, &m.qm, p.q, 2, dims, st, bqm, QBOX ? CU_TENSOR_MAP_SWIZZLE_NONE : CU_TENSOR_MAP_SWIZZLE_128B);
    encode(fn, &m.qt, p.q, 2, dims, st, bqt, CU_TENSOR_MAP_SWIZZLE_32B);
    encode(fn, &m.om, p.out, 2, dims, st, bom, QBOX ? CU_TENSOR_MAP_SWIZZLE_NONE : CU_TENSOR_MAP_SWIZZLE_128B);
    encode(fn, &m.ot, p.out, 2, dims, st, bot, CU_TENSOR_MAP_SWIZZLE_32B);
  }
  fused_kernel<<<NCTA, NTHR, SMEM_BYTES>>>(m, p);
}
```

```cpp
#include <cuda.h>
#include <cuda_bf16.h>
#include <cuda_runtime.h>
#include <stdint.h>

namespace {

constexpr int SEQ = 2048, DIM = 640, NCTA = 128, NTHR = 512;

#define TRIG_KB 9
#define KV_KB 2
#define DEV_EXIT 0
#define ATT_GATE 0
#define G_AFTER 0
#define FENCE_LO 0
#define FENCE_HI 0
#define PW1 2
#define PW2 1
#define ENDBAR 0
#define PAD_KB 0
#define Y_ALIAS 1
#define NOMB 0
#define SRC_ROT 0
#define WAIT_NS 0
#define WB_TRIG B_USIG
#define G_POS 0
#define TAILF 1
#define T_ISSUE 384
#define T_PF 416
#define T_INIT 448
#define ATT_MERGE 0
#define BMAP 1
#define PRE2 1
#define KV_MIX 0
#define O_DEFER 0
#define TASK0 0x3
#define TASK1 0x52
#define TASK2 0x41
#define HALO_FIRST 1
#define PREV_EARLY 0
#define Y_RB 2
#define O_RB 2
#define O_EAGER 1
#define OP_TRIG B_ATTN
#define FUSE_MIX 1
#define Q_EARLY 1
#define U_TRIM 1
#define Q_SLOT 3
#define G_TMA 1
#define W_RB 1
#define WPF B_S3
#define WPF_LIN 1
#define QBOX 0
#define ACQ 0
#define U_TMA 0
#define U_GATE 0
#define RF_GATE 0
#define WO_TRIG B_WST
#define WL_TRIG B_WOP
#define WO_GATE 4

constexpr uint32_t STAGE_BYTES = 47104, ST_W = 16384, ST_WT = 40960;
constexpr uint32_t O_BYTES = 20480, WO_BYTES = 12800;
constexpr uint32_t OFF_OA = 0;
constexpr uint32_t OFF_QS = Q_SLOT * O_BYTES, OFF_QT = OFF_QS + 16384;
constexpr uint32_t OFF_WC = 81920;
constexpr uint32_t OFF_WA = 94720;
constexpr uint32_t OFF_GATE = 145920;
constexpr uint32_t OFF_TT = 146432;
constexpr uint32_t OFF_KVX = 148480;
constexpr uint32_t OFF_CH3 = 163840;
constexpr uint32_t CH_BYTES = 12288, U_BYTES = 4096;
constexpr uint32_t OFF_FT = 225280, OFF_GT = 229376;
constexpr uint32_t OFF_CH0 = 188416;
constexpr uint32_t OFF_KVS = OFF_CH0, KVS_V = 4480, KVS_BYTES = 8576;
constexpr uint32_t OFF_WS = OFF_WA;
__device__ __forceinline__ uint32_t off_us(int s) { return OFF_CH0 + 4096 * ((0x65320 >> (4 * s)) & 7); }
constexpr uint32_t OFF_YT = 163840;
constexpr uint32_t OFF_BAR = 231936;
constexpr uint32_t SMEM_BYTES = OFF_BAR + 512;

enum : uint32_t {
  B_FULL1 = 0, B_EMPTY1 = 4, B_S3 = 7, B_FULL2 = 52, B_EMPTY2 = 13, B_U = 8, B_GATE = 12, B_HA = 19, B_HB = 20,
  B_ATTN = 21, B_C34 = 22, B_YRB = 23, B_YFULL = 24, B_EPOCH = 25, B_PREP = 26, B_P1 = 27, B_LAST = 28,
  B_E3 = 29, B_OSIG = 30, B_WOP = 31, B_USIG = 32, B_WST = 33, B_KV = 34, B_KVD = 39, B_QF = 17, B_ATT2 = 18, B_YST = 40,
  B_ORB = 45, B_CVD = 33 + 14, B_US = 45, B_YSIG = 50
};
constexpr uint32_t OFF_EPOCH = OFF_BAR + 8 * 51, OFF_D = OFF_BAR + 8 * 60;
__device__ __forceinline__ uint32_t off_o(int j) { return j < 4 ? OFF_OA + j * O_BYTES : j < 6 ? OFF_CH0 + (j - 4) * O_BYTES : OFF_OA + (j - 6) * O_BYTES; }
__device__ __forceinline__ uint32_t off_w(int j) { return j < 4 ? OFF_WA + j * WO_BYTES : j == 4 ? OFF_KVX : j == 5 ? OFF_WC : OFF_WA + (j - 6) * WO_BYTES; }
__device__ __forceinline__ int step_src(int hg, int j) {
  if (SRC_ROT == 2) {
    const int pos = (0x37621540 >> (4 * hg)) & 7;
    return j == 0 ? hg : (0x65217430 >> (4 * (j <= pos ? j - 1 : j))) & 7;
  }
  return SRC_ROT ? (hg + j) & 7 : j == 0 ? hg : j <= hg ? j - 1 : j;
}
__device__ __forceinline__ bool tail_first(int hg) { return TAILF && (hg & 3) == 3; }
__device__ __forceinline__ uint32_t off_ch(int c) { return (c < 3 ? OFF_CH0 : OFF_CH3 - 3 * CH_BYTES) + c * CH_BYTES; }

#define U_PITCH 264
__device__ __align__(1024) uint4 g_U[DIM * U_PITCH];
__device__ uint4 g_O[NCTA * 1280];
#define g_Y g_U
constexpr int Y_PITCH = U_PITCH;
__device__ uint4 g_WO[64 * 800];
__device__ uint4 g_halo[NCTA * 2 * 7 * 32];
__device__ __align__(128) float g_gate[SEQ + PAD_KB * 256];
__device__ unsigned g_cnt[32 * (1 + 2 * 16 + 8 + NCTA)];
constexpr int C_LAUNCH = 0, C_PREP = 32, C_Y = 32 * 17, C_W = 32 * 33, C_O = 32 * 41;

#define TSM(cond, slot) do { } while (0)
#define TSIF(cond, slot) do { if (__LINE__ >= FENCE_LO && __LINE__ < FENCE_HI) sched_fence(); } while (0)
__device__ __forceinline__ void sched_fence() {
  asm volatile("{\n.reg .pred p;\n.reg .u32 c;\nmov.u32 c, %%clock;\nsetp.eq.u32 p, c, 0;\n@p st.shared.u32 [%0], c;\n}"
               ::"r"(1024 + OFF_EPOCH + 4) : "memory");
}
#define TS(slot) TSIF(true, slot)

struct Params {
  const __nv_bfloat16 *q, *k, *v, *shift_k, *ssm_k, *ssm_D, *wqkv, *wo, *gate_w;
  __nv_bfloat16* out;
  uint32_t zero;
};

#define POLL_NS 0
constexpr int SPIN_LIMIT = 1 << 17;

__device__ __forceinline__ void mbar_init(uint32_t bar, uint32_t count) {
  asm volatile("mbarrier.init.shared::cta.b64 [%0], %1;" ::"r"(bar), "r"(count) : "memory");
}
__device__ __forceinline__ void mbar_expect_tx(uint32_t bar, uint32_t bytes) {
  asm volatile("mbarrier.arrive.expect_tx.shared::cta.b64 _, [%0], %1;" ::"r"(bar), "r"(bytes) : "memory");
}
__device__ __forceinline__ void mbar_arrive(uint32_t bar) {
  asm volatile("mbarrier.arrive.shared::cta.b64 _, [%0];" ::"r"(bar) : "memory");
}
__device__ __forceinline__ void mbar_wait(uint32_t bar, uint32_t parity) {
  uint32_t ok;
  int spins = 0;
  do {
    if (WAIT_NS)
      asm volatile("{\n.reg .pred p;\nmbarrier.try_wait.parity.shared::cta.b64 p, [%1], %2, %3;\nselp.b32 %0, 1, 0, p;\n}"
                   : "=r"(ok) : "r"(bar), "r"(parity), "r"(WAIT_NS) : "memory");
    else
      asm volatile("{\n.reg .pred p;\nmbarrier.try_wait.parity.shared::cta.b64 p, [%1], %2;\nselp.b32 %0, 1, 0, p;\n}"
                   : "=r"(ok) : "r"(bar), "r"(parity) : "memory");
    if (++spins > SPIN_LIMIT) break;
  } while (!ok);
}
__device__ __forceinline__ unsigned flag_read(const unsigned* p) {
  unsigned v;
  asm volatile("ld.relaxed.gpu.global.u32 %0, [%1];" : "=r"(v) : "l"(p) : "memory");
  return v;
}
__device__ __forceinline__ void flag_poll(const unsigned* p, unsigned target) {
  unsigned v;
  int spins = 0;
  do {
    if (POLL_NS && spins) __nanosleep(POLL_NS);
    asm volatile("ld.relaxed.gpu.global.u32 %0, [%1];" : "=r"(v) : "l"(p) : "memory");
    if (++spins > SPIN_LIMIT) break;
  } while ((int)(v - target) < 0);
}
__device__ __forceinline__ void flag_wait(const unsigned* p, unsigned target) {
  flag_poll(p, target);
  if (ACQ) asm volatile("fence.acquire.gpu;\nfence.proxy.async.global;" ::: "memory");
}
__device__ __forceinline__ void flag_signal(unsigned* p, int n, int lane) {
  if (lane == 0) asm volatile("fence.release.gpu;" ::: "memory");
  __syncwarp();
  if (lane < n) asm volatile("red.relaxed.gpu.global.add.u32 [%0], 1;" ::"l"(p + 32 * lane) : "memory");
}
__device__ __forceinline__ void flag_bump(unsigned* p) {
  asm volatile("red.relaxed.gpu.global.add.u32 [%0], 1;" ::"l"(p) : "memory");
}
__device__ __forceinline__ void fence_async_smem() { asm volatile("fence.proxy.async.shared::cta;" ::: "memory"); }
__device__ __forceinline__ void wg_sync(int id) { asm volatile("bar.sync %0, 128;" ::"r"(id) : "memory"); }

__device__ __forceinline__ void tma_2d(uint32_t dst, const CUtensorMap* tm, int c0, int c1, uint32_t bar) {
  asm volatile("cp.async.bulk.tensor.2d.shared::cluster.global.mbarrier::complete_tx::bytes [%0], [%1, {%3, %4}], [%2];"
               ::"r"(dst), "l"(tm), "r"(bar), "r"(c0), "r"(c1) : "memory");
}
__device__ __forceinline__ void tma_3d(uint32_t dst, const CUtensorMap* tm, int c0, int c1, int c2, uint32_t bar) {
  asm volatile("cp.async.bulk.tensor.3d.shared::cluster.global.mbarrier::complete_tx::bytes [%0], [%1, {%3, %4, %5}], [%2];"
               ::"r"(dst), "l"(tm), "r"(bar), "r"(c0), "r"(c1), "r"(c2) : "memory");
}
__device__ __forceinline__ void bulk_load(uint32_t dst, const void* src, uint32_t bytes, uint32_t bar) {
  asm volatile("cp.async.bulk.shared::cluster.global.mbarrier::complete_tx::bytes [%0], [%1], %2, [%3];"
               ::"r"(dst), "l"(src), "r"(bytes), "r"(bar) : "memory");
}
__device__ __forceinline__ void tm_prefetch(const CUtensorMap* tm) {
  asm volatile("prefetch.tensormap [%0];" ::"l"(tm) : "memory");
}

__device__ __forceinline__ void wg_fence() { asm volatile("wgmma.fence.sync.aligned;" ::: "memory"); }
__device__ __forceinline__ void wg_commit() { asm volatile("wgmma.commit_group.sync.aligned;" ::: "memory"); }
template <int N> __device__ __forceinline__ void wg_wait() { asm volatile("wgmma.wait_group.sync.aligned %0;" ::"n"(N) : "memory"); }
__device__ __forceinline__ uint32_t desc_lo(uint32_t addr, uint32_t lbo) { return ((addr & 0x3FFFF) >> 4) | ((lbo >> 4) << 16); }
constexpr uint32_t desc_hi(uint32_t sbo, uint32_t swz) { return (sbo >> 4) | (swz << 30); }
constexpr uint32_t HI_SW128 = desc_hi(1024, 1), HI_SW64 = desc_hi(512, 2), HI_SW32 = desc_hi(256, 3), HI_NONE = desc_hi(128, 0);
template <int N> __device__ __forceinline__ void pin(float* d) {
#pragma unroll
  for (int i = 0; i < N; i++) asm volatile("" : "+f"(d[i])::"memory");
}

__device__ __forceinline__ uint32_t lds32(uint32_t a) {
  uint32_t v;
  asm volatile("ld.volatile.shared.u32 %0, [%1];" : "=r"(v) : "r"(a) : "memory");
  return v;
}
__device__ __forceinline__ uint4 ldg128(const void* a) {
  uint4 v;
  asm volatile("ld.global.nc.v4.u32 {%0, %1, %2, %3}, [%4];" : "=r"(v.x), "=r"(v.y), "=r"(v.z), "=r"(v.w) : "l"(a) : "memory");
  return v;
}
__device__ __forceinline__ uint2 ldg64(const void* a) {
  uint2 v;
  asm volatile("ld.global.nc.v2.u32 {%0, %1}, [%2];" : "=r"(v.x), "=r"(v.y) : "l"(a) : "memory");
  return v;
}
__device__ __forceinline__ void ldsm4(uint32_t* r, uint32_t a) {
  asm volatile("ldmatrix.sync.aligned.m8n8.x4.shared.b16 {%0, %1, %2, %3}, [%4];"
               : "=r"(r[0]), "=r"(r[1]), "=r"(r[2]), "=r"(r[3]) : "r"(a) : "memory");
}
__device__ __forceinline__ void ldsm4t(uint32_t* r, uint32_t a) {
  asm volatile("ldmatrix.sync.aligned.m8n8.x4.trans.shared.b16 {%0, %1, %2, %3}, [%4];"
               : "=r"(r[0]), "=r"(r[1]), "=r"(r[2]), "=r"(r[3]) : "r"(a) : "memory");
}
__device__ __forceinline__ uint2 lds64(uint32_t a) {
  uint2 v;
  asm volatile("ld.shared.v2.u32 {%0, %1}, [%2];" : "=r"(v.x), "=r"(v.y) : "r"(a) : "memory");
  return v;
}
__device__ __forceinline__ uint4 lds128(uint32_t a) {
  uint4 v;
  asm volatile("ld.shared.v4.u32 {%0, %1, %2, %3}, [%4];" : "=r"(v.x), "=r"(v.y), "=r"(v.z), "=r"(v.w) : "r"(a) : "memory");
  return v;
}
__device__ __forceinline__ void sts128(uint32_t a, uint32_t x, uint32_t y, uint32_t z, uint32_t w) {
  asm volatile("st.shared.v4.u32 [%0], {%1, %2, %3, %4};" ::"r"(a), "r"(x), "r"(y), "r"(z), "r"(w) : "memory");
}
__device__ __forceinline__ void stsm4(uint32_t a, const uint32_t* r) {
  asm volatile("stmatrix.sync.aligned.m8n8.x4.shared.b16 [%0], {%1, %2, %3, %4};" ::"r"(a), "r"(r[0]), "r"(r[1]), "r"(r[2]), "r"(r[3]) : "memory");
}
__device__ __forceinline__ void stsm4t(uint32_t a, const uint32_t* r) {
  asm volatile("stmatrix.sync.aligned.m8n8.x4.trans.shared.b16 [%0], {%1, %2, %3, %4};" ::"r"(a), "r"(r[0]), "r"(r[1]), "r"(r[2]), "r"(r[3]) : "memory");
}
__device__ __forceinline__ uint32_t pack2(float lo, float hi) {
  uint32_t r;
  asm("cvt.rn.bf16x2.f32 %0, %1, %2;" : "=r"(r) : "f"(hi), "f"(lo));
  return r;
}
__device__ __forceinline__ uint32_t movm(uint32_t a) {
  uint32_t d;
  asm volatile("movmatrix.sync.aligned.m8n8.trans.b16 %0, %1;" : "=r"(d) : "r"(a));
  return d;
}
__device__ __forceinline__ uint32_t bmul(uint32_t a, uint32_t b) {
  uint32_t d;
  asm("mul.rn.bf16x2 %0, %1, %2;" : "=r"(d) : "r"(a), "r"(b));
  return d;
}
__device__ __forceinline__ uint32_t badd(uint32_t a, uint32_t b) {
  uint32_t d;
  asm("add.rn.bf16x2 %0, %1, %2;" : "=r"(d) : "r"(a), "r"(b));
  return d;
}
__device__ __forceinline__ uint32_t bfma(uint32_t a, uint32_t b, uint32_t c) {
  uint32_t d;
  asm("fma.rn.bf16x2 %0, %1, %2, %3;" : "=r"(d) : "r"(a), "r"(b), "r"(c));
  return d;
}
__device__ __forceinline__ float bf_lo(uint32_t x) { return __uint_as_float(x << 16); }
__device__ __forceinline__ float bf_hi(uint32_t x) { return __uint_as_float(x & 0xFFFF0000u); }
__device__ __forceinline__ float ex2(float x) {
  float y;
  asm("ex2.approx.ftz.f32 %0, %1;" : "=f"(y) : "f"(x));
  return y;
}
__device__ __forceinline__ float rcp(float x) {
  float y;
  asm("rcp.approx.ftz.f32 %0, %1;" : "=f"(y) : "f"(x));
  return y;
}
__device__ __forceinline__ void mma16816(float* d, uint32_t a0, uint32_t a1, uint32_t a2, uint32_t a3, uint32_t b0, uint32_t b1) {
  asm volatile("mma.sync.aligned.m16n8k16.row.col.f32.bf16.bf16.f32 {%0, %1, %2, %3}, {%4, %5, %6, %7}, {%8, %9}, {%0, %1, %2, %3};"
               : "+f"(d[0]), "+f"(d[1]), "+f"(d[2]), "+f"(d[3])
               : "r"(a0), "r"(a1), "r"(a2), "r"(a3), "r"(b0), "r"(b1));
}
__device__ __forceinline__ void mma1688(float* d, uint32_t a0, uint32_t a1, uint32_t b0) {
  asm volatile("mma.sync.aligned.m16n8k8.row.col.f32.bf16.bf16.f32 {%0, %1, %2, %3}, {%4, %5}, {%6}, {%0, %1, %2, %3};"
               : "+f"(d[0]), "+f"(d[1]), "+f"(d[2]), "+f"(d[3])
               : "r"(a0), "r"(a1), "r"(b0));
}

template <int N> struct WgRS;
template <int N> struct WgSST;
template <> struct WgRS<32> {
  template <uint32_t HB>
  static __device__ __forceinline__ void mma(float* d, const uint32_t* a, uint32_t db) {
    asm volatile("{\n.reg .pred p;\n.reg .b64 db;\nsetp.ne.b32 p, %22, 0;\n"
      "mov.b64 db, {%20, %21};\n"
      "wgmma.mma_async.sync.aligned.m64n32k16.f32.bf16.bf16 {"
      "%0, %1, %2, %3, %4, %5, %6, %7, %8, %9, %10, %11, %12, %13, %14, %15"
      "}, {%16, %17, %18, %19}, db, p, 1, 1, 1;\n}\n"
      : "+f"(d[0]), "+f"(d[1]), "+f"(d[2]), "+f"(d[3]), "+f"(d[4]), "+f"(d[5]), "+f"(d[6]), "+f"(d[7]),
        "+f"(d[8]), "+f"(d[9]), "+f"(d[10]), "+f"(d[11]), "+f"(d[12]), "+f"(d[13]), "+f"(d[14]), "+f"(d[15])
      : "r"(a[0]), "r"(a[1]), "r"(a[2]), "r"(a[3]), "r"(db), "n"(HB), "n"(1));
  }
  template <uint32_t HB>
  static __device__ __forceinline__ void set(float* d, const uint32_t* a, uint32_t db) {
    asm volatile("{\n.reg .pred p;\n.reg .b64 db;\nsetp.ne.b32 p, %22, 0;\n"
      "mov.b64 db, {%20, %21};\n"
      "wgmma.mma_async.sync.aligned.m64n32k16.f32.bf16.bf16 {"
      "%0, %1, %2, %3, %4, %5, %6, %7, %8, %9, %10, %11, %12, %13, %14, %15"
      "}, {%16, %17, %18, %19}, db, p, 1, 1, 1;\n}\n"
      : "=f"(d[0]), "=f"(d[1]), "=f"(d[2]), "=f"(d[3]), "=f"(d[4]), "=f"(d[5]), "=f"(d[6]), "=f"(d[7]),
        "=f"(d[8]), "=f"(d[9]), "=f"(d[10]), "=f"(d[11]), "=f"(d[12]), "=f"(d[13]), "=f"(d[14]), "=f"(d[15])
      : "r"(a[0]), "r"(a[1]), "r"(a[2]), "r"(a[3]), "r"(db), "n"(HB), "n"(0));
  }
};
template <> struct WgRS<64> {
  template <uint32_t HB>
  static __device__ __forceinline__ void mma(float* d, const uint32_t* a, uint32_t db) {
    asm volatile("{\n.reg .pred p;\n.reg .b64 db;\nsetp.ne.b32 p, %38, 0;\n"
      "mov.b64 db, {%36, %37};\n"
      "wgmma.mma_async.sync.aligned.m64n64k16.f32.bf16.bf16 {"
      "%0, %1, %2, %3, %4, %5, %6, %7, %8, %9, %10, %11, %12, %13, %14, %15, "
      "%16, %17, %18, %19, %20, %21, %22, %23, %24, %25, %26, %27, %28, %29, %30, %31"
      "}, {%32, %33, %34, %35}, db, p, 1, 1, 1;\n}\n"
      : "+f"(d[0]), "+f"(d[1]), "+f"(d[2]), "+f"(d[3]), "+f"(d[4]), "+f"(d[5]), "+f"(d[6]), "+f"(d[7]),
        "+f"(d[8]), "+f"(d[9]), "+f"(d[10]), "+f"(d[11]), "+f"(d[12]), "+f"(d[13]), "+f"(d[14]), "+f"(d[15]),
        "+f"(d[16]), "+f"(d[17]), "+f"(d[18]), "+f"(d[19]), "+f"(d[20]), "+f"(d[21]), "+f"(d[22]), "+f"(d[23]),
        "+f"(d[24]), "+f"(d[25]), "+f"(d[26]), "+f"(d[27]), "+f"(d[28]), "+f"(d[29]), "+f"(d[30]), "+f"(d[31])
      : "r"(a[0]), "r"(a[1]), "r"(a[2]), "r"(a[3]), "r"(db), "n"(HB), "n"(1));
  }
  template <uint32_t HB>
  static __device__ __forceinline__ void set(float* d, const uint32_t* a, uint32_t db) {
    asm volatile("{\n.reg .pred p;\n.reg .b64 db;\nsetp.ne.b32 p, %38, 0;\n"
      "mov.b64 db, {%36, %37};\n"
      "wgmma.mma_async.sync.aligned.m64n64k16.f32.bf16.bf16 {"
      "%0, %1, %2, %3, %4, %5, %6, %7, %8, %9, %10, %11, %12, %13, %14, %15, "
      "%16, %17, %18, %19, %20, %21, %22, %23, %24, %25, %26, %27, %28, %29, %30, %31"
      "}, {%32, %33, %34, %35}, db, p, 1, 1, 1;\n}\n"
      : "=f"(d[0]), "=f"(d[1]), "=f"(d[2]), "=f"(d[3]), "=f"(d[4]), "=f"(d[5]), "=f"(d[6]), "=f"(d[7]),
        "=f"(d[8]), "=f"(d[9]), "=f"(d[10]), "=f"(d[11]), "=f"(d[12]), "=f"(d[13]), "=f"(d[14]), "=f"(d[15]),
        "=f"(d[16]), "=f"(d[17]), "=f"(d[18]), "=f"(d[19]), "=f"(d[20]), "=f"(d[21]), "=f"(d[22]), "=f"(d[23]),
        "=f"(d[24]), "=f"(d[25]), "=f"(d[26]), "=f"(d[27]), "=f"(d[28]), "=f"(d[29]), "=f"(d[30]), "=f"(d[31])
      : "r"(a[0]), "r"(a[1]), "r"(a[2]), "r"(a[3]), "r"(db), "n"(HB), "n"(0));
  }
};
template <> struct WgSST<48> {
  template <uint32_t HA, uint32_t HB>
  static __device__ __forceinline__ void mma(float* d, uint32_t da, uint32_t db, int sc) {
    asm volatile("{\n.reg .pred p;\n.reg .b64 da, db;\nsetp.ne.b32 p, %28, 0;\n"
      "mov.b64 da, {%24, %25};\nmov.b64 db, {%26, %27};\n"
      "wgmma.mma_async.sync.aligned.m64n48k16.f32.bf16.bf16 {"
      "%0, %1, %2, %3, %4, %5, %6, %7, %8, %9, %10, %11, %12, %13, %14, %15, "
      "%16, %17, %18, %19, %20, %21, %22, %23"
      "}, da, db, p, 1, 1, 0, 1;\n}\n"
      : "+f"(d[0]), "+f"(d[1]), "+f"(d[2]), "+f"(d[3]), "+f"(d[4]), "+f"(d[5]), "+f"(d[6]), "+f"(d[7]),
        "+f"(d[8]), "+f"(d[9]), "+f"(d[10]), "+f"(d[11]), "+f"(d[12]), "+f"(d[13]), "+f"(d[14]), "+f"(d[15]),
        "+f"(d[16]), "+f"(d[17]), "+f"(d[18]), "+f"(d[19]), "+f"(d[20]), "+f"(d[21]), "+f"(d[22]), "+f"(d[23])
      : "r"(da), "n"(HA), "r"(db), "n"(HB), "r"(sc));
  }
};
template <> struct WgSST<80> {
  template <uint32_t HA, uint32_t HB>
  static __device__ __forceinline__ void mma(float* d, uint32_t da, uint32_t db, int sc) {
    asm volatile("{\n.reg .pred p;\n.reg .b64 da, db;\nsetp.ne.b32 p, %44, 0;\n"
      "mov.b64 da, {%40, %41};\nmov.b64 db, {%42, %43};\n"
      "wgmma.mma_async.sync.aligned.m64n80k16.f32.bf16.bf16 {"
      "%0, %1, %2, %3, %4, %5, %6, %7, %8, %9, %10, %11, %12, %13, %14, %15, "
      "%16, %17, %18, %19, %20, %21, %22, %23, %24, %25, %26, %27, %28, %29, %30, %31, "
      "%32, %33, %34, %35, %36, %37, %38, %39"
      "}, da, db, p, 1, 1, 0, 1;\n}\n"
      : "+f"(d[0]), "+f"(d[1]), "+f"(d[2]), "+f"(d[3]), "+f"(d[4]), "+f"(d[5]), "+f"(d[6]), "+f"(d[7]),
        "+f"(d[8]), "+f"(d[9]), "+f"(d[10]), "+f"(d[11]), "+f"(d[12]), "+f"(d[13]), "+f"(d[14]), "+f"(d[15]),
        "+f"(d[16]), "+f"(d[17]), "+f"(d[18]), "+f"(d[19]), "+f"(d[20]), "+f"(d[21]), "+f"(d[22]), "+f"(d[23]),
        "+f"(d[24]), "+f"(d[25]), "+f"(d[26]), "+f"(d[27]), "+f"(d[28]), "+f"(d[29]), "+f"(d[30]), "+f"(d[31]),
        "+f"(d[32]), "+f"(d[33]), "+f"(d[34]), "+f"(d[35]), "+f"(d[36]), "+f"(d[37]), "+f"(d[38]), "+f"(d[39])
      : "r"(da), "n"(HA), "r"(db), "n"(HB), "r"(sc));
  }
};
template <> struct WgSST<192> {
  template <uint32_t HA, uint32_t HB>
  static __device__ __forceinline__ void mma(float* d, uint32_t da, uint32_t db, int sc) {
    asm volatile("{\n.reg .pred p;\n.reg .b64 da, db;\nsetp.ne.b32 p, %100, 0;\n"
      "mov.b64 da, {%96, %97};\nmov.b64 db, {%98, %99};\n"
      "wgmma.mma_async.sync.aligned.m64n192k16.f32.bf16.bf16 {"
      "%0, %1, %2, %3, %4, %5, %6, %7, %8, %9, %10, %11, %12, %13, %14, %15, "
      "%16, %17, %18, %19, %20, %21, %22, %23, %24, %25, %26, %27, %28, %29, %30, %31, "
      "%32, %33, %34, %35, %36, %37, %38, %39, %40, %41, %42, %43, %44, %45, %46, %47, "
      "%48, %49, %50, %51, %52, %53, %54, %55, %56, %57, %58, %59, %60, %61, %62, %63, "
      "%64, %65, %66, %67, %68, %69, %70, %71, %72, %73, %74, %75, %76, %77, %78, %79, "
      "%80, %81, %82, %83, %84, %85, %86, %87, %88, %89, %90, %91, %92, %93, %94, %95"
      "}, da, db, p, 1, 1, 0, 1;\n}\n"
      : "+f"(d[0]), "+f"(d[1]), "+f"(d[2]), "+f"(d[3]), "+f"(d[4]), "+f"(d[5]), "+f"(d[6]), "+f"(d[7]),
        "+f"(d[8]), "+f"(d[9]), "+f"(d[10]), "+f"(d[11]), "+f"(d[12]), "+f"(d[13]), "+f"(d[14]), "+f"(d[15]),
        "+f"(d[16]), "+f"(d[17]), "+f"(d[18]), "+f"(d[19]), "+f"(d[20]), "+f"(d[21]), "+f"(d[22]), "+f"(d[23]),
        "+f"(d[24]), "+f"(d[25]), "+f"(d[26]), "+f"(d[27]), "+f"(d[28]), "+f"(d[29]), "+f"(d[30]), "+f"(d[31]),
        "+f"(d[32]), "+f"(d[33]), "+f"(d[34]), "+f"(d[35]), "+f"(d[36]), "+f"(d[37]), "+f"(d[38]), "+f"(d[39]),
        "+f"(d[40]), "+f"(d[41]), "+f"(d[42]), "+f"(d[43]), "+f"(d[44]), "+f"(d[45]), "+f"(d[46]), "+f"(d[47]),
        "+f"(d[48]), "+f"(d[49]), "+f"(d[50]), "+f"(d[51]), "+f"(d[52]), "+f"(d[53]), "+f"(d[54]), "+f"(d[55]),
        "+f"(d[56]), "+f"(d[57]), "+f"(d[58]), "+f"(d[59]), "+f"(d[60]), "+f"(d[61]), "+f"(d[62]), "+f"(d[63]),
        "+f"(d[64]), "+f"(d[65]), "+f"(d[66]), "+f"(d[67]), "+f"(d[68]), "+f"(d[69]), "+f"(d[70]), "+f"(d[71]),
        "+f"(d[72]), "+f"(d[73]), "+f"(d[74]), "+f"(d[75]), "+f"(d[76]), "+f"(d[77]), "+f"(d[78]), "+f"(d[79]),
        "+f"(d[80]), "+f"(d[81]), "+f"(d[82]), "+f"(d[83]), "+f"(d[84]), "+f"(d[85]), "+f"(d[86]), "+f"(d[87]),
        "+f"(d[88]), "+f"(d[89]), "+f"(d[90]), "+f"(d[91]), "+f"(d[92]), "+f"(d[93]), "+f"(d[94]), "+f"(d[95])
      : "r"(da), "n"(HA), "r"(db), "n"(HB), "r"(sc));
  }
};

struct FftConst {
  uint32_t f[2][4], fi[4][4];
  uint32_t ta[2][2], tb[2][2];
};
__device__ __forceinline__ void cis(int m, float scale, float& c, float& s) {
  const float a = (float)m * (-6.283185307179586f * scale);
  c = __cosf(a);
  s = __sinf(a);
}
__device__ __forceinline__ void fft_tables(uint32_t (&v)[12], int tw) {
  const int row = tw >> 2, ch = tw & 3;
#pragma unroll
  for (int i = 0; i < 4; i++) {
    float c[2], s[2], x[2];
#pragma unroll
    for (int e = 0; e < 2; e++) {
      cis((((32 * (8 * ch + 2 * i + e) + 15) * (4 * row - 63) + 2048) & 4095) - 2048, 1.f / 4096, c[e], s[e]);
      float gc, gs;
      cis((((row & 15) * (8 * (ch & 1) + 2 * i + e) + 8) & 15) - 8, 1.f / 16, gc, gs);
      x[e] = (row >> 4) == (ch >> 1) ? gc : (ch >> 1) ? gs : -gs;
    }
    v[i] = pack2(c[0] * 0.125f, c[1] * 0.125f);
    v[4 + i] = pack2(s[0] * 0.125f, s[1] * 0.125f);
    v[8 + i] = pack2(x[0], x[1]);
  }
#pragma unroll
  for (int i = 0; i < 12; i++) asm volatile("" : "+r"(v[i]));
}
__device__ __forceinline__ void fft_tables_store(const uint32_t (&v)[12], uint32_t sb, int tw) {
  const int row = tw >> 2;
  const uint32_t x = ((tw ^ (row >> 1)) & 3) << 4, a = sb + OFF_FT + (16 * (row >> 3) + (row & 7)) * 64 + x;
  sts128(a, v[0], v[1], v[2], v[3]);
  sts128(a + 512, v[4], v[5], v[6], v[7]);
  sts128(sb + OFF_GT + row * 64 + x, v[8], v[9], v[10], v[11]);
}
__device__ __forceinline__ void fft_twiddles(uint32_t (&v)[2], int tw) {
  float a[2], s[2];
#pragma unroll
  for (int i = 0; i < 2; i++) {
    float c;
    cis((2 * (2 * (tw & 3) + i) - 15) * (4 * (tw >> 2) - 63), 1.f / 4096, c, s[i]);
    a[i] = __fdividef(-s[i], 1.f + c);
  }
  v[0] = pack2(a[0], a[1]);
  v[1] = pack2(s[0], s[1]);
  asm volatile("" : "+r"(v[0]), "+r"(v[1]));
}
__device__ __forceinline__ void fft_matrices(FftConst& k, uint32_t sb, int w, int lane) {
  const uint32_t x = (lane >> 1) & 3;
  const uint2 t0 = lds64(sb + OFF_TT + 256 * w + 8 * lane), t1 = lds64(sb + OFF_TT + 256 * w + 8 * (lane ^ 3));
  k.ta[0][0] = t0.x;
  k.tb[0][0] = t0.y;
  k.ta[1][1] = __byte_perm(t1.x, 0, 0x1032);
  k.tb[1][1] = __byte_perm(t1.y, 0, 0x1032);
#pragma unroll
  for (int j = 0; j < 2; j++) {
    k.ta[1 - j][j] = k.ta[j][j] ^ 0x80008000u;
    k.tb[1 - j][j] = k.tb[j][j] ^ 0x80008000u;
    asm volatile("" : "+r"(k.ta[0][j]), "+r"(k.tb[0][j]), "+r"(k.ta[1][j]), "+r"(k.tb[1][j]));
  }
#pragma unroll
  for (int i = 0; i < 2; i++) {
    ldsm4(k.f[i], sb + OFF_FT + (16 * w + (lane & 15)) * 64 + (((2 * i + (lane >> 4)) ^ x) << 4));
    ldsm4t(k.fi[i], sb + OFF_FT + (32 * i + lane) * 64 + ((w ^ x) << 4));
#pragma unroll
    for (int j = 0; j < 4; j++) {
      k.fi[2 + i][j] = (j & 1) ? k.fi[i][j - 1] ^ 0x80008000u : k.fi[i][j + 1];
      asm volatile("" : "+r"(k.fi[2 + i][j]));
    }
  }
}
__device__ __forceinline__ void rot(uint32_t& x, uint32_t& y, uint32_t a, uint32_t b) {
  x = bfma(a, y, x);
  y = bfma(b, x, y);
  x = bfma(a, y, x);
}
__device__ __forceinline__ void twiddle_fwd(uint32_t (&a)[4][4], float* d, const FftConst& k) {
#pragma unroll
  for (int q = 0; q < 4; q++)
#pragma unroll
    for (int j = 0; j < 2; j++) {
      const float* x = d + 8 * q + 4 * j;
      uint32_t re = pack2(x[0], x[1]), im = pack2(x[2], x[3]);
      rot(re, im, k.ta[0][j], k.tb[0][j]);
      a[q & 2][2 * j + (q & 1)] = re;
      a[(q & 2) + 1][2 * j + (q & 1)] = im;
    }
}
__device__ __forceinline__ void g_step(float* d, const uint32_t (&a)[4][4], uint32_t dre, uint32_t dim) {
  WgRS<32>::set<HI_SW64>(d, a[0], dre);
  WgRS<32>::set<HI_SW64>(d + 16, a[2], dre);
  WgRS<32>::mma<HI_SW64>(d, a[1], dim);
  WgRS<32>::mma<HI_SW64>(d + 16, a[3], dim);
  wg_commit();
}

__device__ __forceinline__ void products(uint32_t (&a)[4][4], const float* H, const float* U, int p) {
#pragma unroll
  for (int j = 0; j < 2; j++)
#pragma unroll
    for (int m = 2 * p; m < 2 * p + 2; m++) {
      float pr[2], pi[2];
#pragma unroll
      for (int x = 0; x < 2; x++)
#pragma unroll
        for (int q = 0; q <= m; q++) {
          const int ih = 16 * (q >> 1) + 2 * (q & 1) + 4 * j + x, iu = 16 * ((m - q) >> 1) + 2 * ((m - q) & 1) + 4 * j + x;
          pr[x] = q ? fmaf(H[ih], U[iu], pr[x]) : H[ih] * U[iu];
          pi[x] = q ? fmaf(H[ih], U[iu + 8], pi[x]) : H[ih] * U[iu + 8];
          pr[x] = fmaf(-H[ih + 8], U[iu + 8], pr[x]);
          pi[x] = fmaf(H[ih + 8], U[iu], pi[x]);
        }
      a[m & 2][2 * j + (m & 1)] = pack2(pr[0], pr[1]);
      a[(m & 2) + 1][2 * j + (m & 1)] = pack2(pi[0], pi[1]);
    }
}

__device__ __forceinline__ void f_step(float* d, const FftConst& k, uint32_t db) {
  WgRS<64>::set<HI_SW32>(d, k.f[0], db);
  WgRS<64>::mma<HI_SW32>(d, k.f[1], db + 32);
  wg_commit();
}
__device__ __forceinline__ void last_step(float* d, const FftConst& k, uint32_t dz) {
  wg_fence();
  WgRS<64>::set<HI_SW128>(d, k.fi[0], dz);
#pragma unroll
  for (int ks = 1; ks < 4; ks++) WgRS<64>::mma<HI_SW128>(d, k.fi[ks], dz + 128 * ks);
  wg_commit();
}
__device__ __forceinline__ void conv_channel(const FftConst& k, uint32_t (&a)[4][4], uint32_t sb, int c, int cn, int wg, int w, int lane) {
  const uint32_t cb = sb + off_ch(c), bars = sb + OFF_BAR;
  const uint32_t du = desc_lo(cb, 1024), dg = desc_lo(sb + OFF_GT, 16), dz = desc_lo(cb + U_BYTES, 16);
  float U[32], H[32];
  uint32_t e[4][4];
  const float dv = __uint_as_float(lds32(sb + OFF_D + 4 * c));
  if (ATT_GATE) mbar_wait(bars + 8 * (ATT_GATE == 1 ? B_ATTN : B_ATT2), 0);
  mbar_wait(bars + 8 * (B_U + (c < 3 ? c : 3)), 0);
  TSM(w == 0 && c < 3, 7 + wg);
  wg_fence();
  f_step(U, k, du);
  g_step(H, a, dg, dg + 64);
  wg_wait<1>();
  pin<32>(U);
  twiddle_fwd(e, U, k);
  wg_fence();
  g_step(U, e, dg, dg + 64);
  wg_wait<0>();
  pin<32>(U);
  pin<32>(H);
#pragma unroll
  for (int j = 0; j < 4; j++) H[4 * (j >> 1) + (j & 1)] += dv;
  float V[32];
#pragma unroll
  for (int p = 0; p < 2; p++) {
    products(a, H, U, p);
    wg_fence();
    WgRS<32>::set<HI_SW64>(V + 16 * p, a[2 * p], dg + 64);
    WgRS<32>::mma<HI_SW64>(V + 16 * p, a[2 * p + 1], dg);
    wg_commit();
  }
  const uint32_t za = cb + U_BYTES + (8 * w + (lane & 7)) * 128 + (((lane >> 3) ^ (lane & 7)) << 4);
  const uint32_t ya = cb + (lane >> 4) * 1024 + (8 * w + (lane & 7)) * 32 + ((((lane >> 3) ^ (lane >> 2)) & 1) << 4);
  wg_sync(1 + wg);
#pragma unroll
  for (int p = 0; p < 2; p++) {
    if (p == 0) wg_wait<1>();
    else wg_wait<0>();
    pin<16>(V + 16 * p);
#pragma unroll
    for (int i = 0; i < 4; i++) {
      const int j = i & 1;
      const float* x = V + 16 * p + 4 * j + (i & 2);
      e[p][i] = pack2(x[8], x[9]);
      e[2 + p][i] = pack2(x[0], x[1]);
      rot(e[p][i], e[2 + p][i], k.ta[1][j], k.tb[1][j]);
    }
    stsm4(za ^ (64 * p), e[p]);
    stsm4((za ^ (64 * p)) + 4096, e[2 + p]);
  }
  if (cn >= 0) {
    wg_fence();
    f_step(U, k, desc_lo(sb + off_ch(cn) + U_BYTES, 1024));
    fence_async_smem();
    wg_sync(1 + wg);
    last_step(H, k, dz);
    wg_wait<1>();
    pin<32>(U);
    twiddle_fwd(a, U, k);
    wg_wait<0>();
  } else {
    fence_async_smem();
    wg_sync(1 + wg);
    last_step(H, k, dz);
    wg_wait<0>();
  }
  pin<32>(H);
  if (WO_GATE == 4 && lane == 0) mbar_arrive(bars + 8 * B_CVD);
  TSIF(w == 0, 88 + c);
#pragma unroll
  for (int j = 0; j < 8; j++)
    e[j >> 2][j & 3] = j < 2 ? pack2(H[4 * j], H[4 * j + 1]) : pack2(H[4 * j] + H[4 * j - 6], H[4 * j + 1] + H[4 * j - 5]);
  stsm4(ya, e[0]);
  stsm4(ya + 2048, e[1]);
  fence_async_smem();
  __syncwarp();
}

__device__ __forceinline__ void prep_slab(uint4* res, const uint2* sw, uint32_t sb, int slab, int w, int lane) {
  const int t = lane & 3, tp = (lane & 7) >> 1, pos = 8 * tp + 2 * (((lane >> 3) + tp) & 3) + (lane & 1);
  const uint32_t base = sb + OFF_KVS + slab * KVS_BYTES + pos * 128;
  uint32_t kk[2][4][4], vv[2][4];
  mbar_wait(sb + OFF_BAR + 8 * (B_KV + slab), 0);
#pragma unroll
  for (int h = 0; h < 2; h++) {
#pragma unroll
    for (int j = 0; j < 4; j++) {
      const uint32_t a = base + 128 * j;
      ldsm4t(kk[h][j], a + (((w + 4 * h) ^ ((a >> 7) & 7)) << 4));
    }
    const uint32_t a = base + KVS_V;
    ldsm4t(vv[h], a + (((w + 4 * h) ^ ((a >> 7) & 7)) << 4));
  }
#pragma unroll
  for (int h = 0; h < 2; h++) {
    uint32_t (&k)[4][4] = kk[h];
    uint32_t (&v)[4] = vv[h];
    const uint32_t w0 = __byte_perm(sw[h].x, 0, 0x1010), w1 = __byte_perm(sw[h].x, 0, 0x3232);
    const uint32_t w2 = __byte_perm(sw[h].y, 0, 0x1010), w3 = __byte_perm(sw[h].y, 0, 0x3232);
#pragma unroll
    for (int m = 0; m < 4; m++)
      v[m] = bmul(badd(badd(badd(bmul(k[0][m], w3), bmul(k[1][m], w2)), bmul(k[2][m], w1)), bmul(k[3][m], w0)), v[m]);
    uint32_t a[4];
#pragma unroll
    for (int m = 0; m < 4; m++) a[m] = (t & 1) ? v[(m + 3) & 3] : v[m];
    res[h] = (t & 2) ? make_uint4(a[2], a[3], a[0], a[1]) : make_uint4(a[0], a[1], a[2], a[3]);
  }
}

__device__ __forceinline__ void prep_gate(const Params& p, uint32_t sb, int b, int w, int lane) {
  uint2 gw[5], x[4][5];
#pragma unroll
  for (int j = 0; j < 5; j++) gw[j] = ldg64(reinterpret_cast<const uint2*>(p.gate_w) + lane + 32 * j);
#pragma unroll
  for (int i = 0; i < 4; i++)
#pragma unroll
    for (int j = 0; j < 5; j++)
      x[i][j] = ldg64(reinterpret_cast<const uint2*>(p.q) + (16 * b + 4 * w + i) * (DIM / 4) + lane + 32 * j);
  float s[4];
#pragma unroll
  for (int i = 0; i < 4; i++) {
    s[i] = 0.f;
#pragma unroll
    for (int j = 0; j < 5; j++) {
      const uint32_t m0 = bmul(x[i][j].x, gw[j].x), m1 = bmul(x[i][j].y, gw[j].y);
      s[i] += (bf_lo(m0) + bf_hi(m0)) + (bf_lo(m1) + bf_hi(m1));
    }
  }
  const bool h = lane & 16, q = lane & 8;
  const float a = (h ? s[2] : s[0]) + __shfl_xor_sync(0xffffffffu, h ? s[0] : s[2], 16);
  const float c = (h ? s[3] : s[1]) + __shfl_xor_sync(0xffffffffu, h ? s[1] : s[3], 16);
  float z = (q ? c : a) + __shfl_xor_sync(0xffffffffu, q ? a : c, 8);
#pragma unroll
  for (int o = 4; o > 0; o >>= 1) z += __shfl_xor_sync(0xffffffffu, z, o);
  z = bf_lo(pack2(z, 0.f));
  z = bf_lo(pack2(__fdividef(1.f, 1.f + __expf(-z)), 0.f));
  if (G_TMA) {
    mbar_wait(sb + OFF_BAR + 8 * B_S3, 0);
    if ((lane & 7) == 0) asm volatile("st.shared.f32 [%0], %1;" ::"r"(sb + OFF_GATE + 64 * (b & 7) + 16 * w + (lane >> 1)), "f"(z) : "memory");
    fence_async_smem();
  } else if ((lane & 7) == 0) {
    g_gate[16 * b + 4 * w + (lane >> 3)] = z;
  }
}

__device__ __forceinline__ uint32_t bmax(uint32_t a, uint32_t b) {
  uint32_t d;
  asm("max.bf16x2 %0, %1, %2;" : "=r"(d) : "r"(a), "r"(b));
  return d;
}
__device__ __forceinline__ void softmax_two(const float (&l)[2][2], uint32_t& p0, uint32_t& p1) {
  constexpr float kScale = 0.22360679774997896f, kLog2e = 1.4426950408889634f;
  const uint32_t r0 = pack2(l[0][0], l[1][0]), r1 = pack2(l[0][1], l[1][1]);
  const uint32_t x0 = pack2(bf_lo(r0) * kScale, bf_hi(r0) * kScale), x1 = pack2(bf_lo(r1) * kScale, bf_hi(r1) * kScale);
  uint32_t m = bmax(x0, x1);
  m = bmax(m, __shfl_xor_sync(0xffffffffu, m, 1));
  m = bmax(m, __shfl_xor_sync(0xffffffffu, m, 2));
  const float m0 = bf_lo(m) * kLog2e, m1 = bf_hi(m) * kLog2e;
  p0 = pack2(ex2(bf_lo(x0) * kLog2e - m0), ex2(bf_lo(x1) * kLog2e - m0));
  p1 = pack2(ex2(bf_hi(x0) * kLog2e - m1), ex2(bf_hi(x1) * kLog2e - m1));
}

__device__ __forceinline__ void halo_read(uint32_t (&kpv)[10], uint32_t (&vpv)[10], uint32_t (&tg)[7], const uint4* hp) {
#pragma unroll
  for (int j = 0; j < 7; j++) {
    uint32_t x0, x1, x2;
    asm volatile("ld.relaxed.gpu.global.v4.u32 {%0, %1, %2, %3}, [%4];"
                 : "=r"(x0), "=r"(x1), "=r"(x2), "=r"(tg[j]) : "l"(hp + 32 * j) : "memory");
    if (j < 4) kpv[3 * j] = x0; else vpv[3 * j - 10] = x0;
    if (j < 3) kpv[3 * j + 1] = x1; else vpv[3 * j - 9] = x1;
    if (j < 3) kpv[3 * j + 2] = x2; else if (j < 6) vpv[3 * j - 8] = x2;
  }
}

template <int ROT>
__device__ __forceinline__ void pack_qkv(const float* acc, uint32_t (&qlo)[10], uint32_t (&qhi)[10], uint32_t (&klo)[10],
                                         uint32_t (&khi)[10], uint32_t (&vlo)[10], uint32_t (&vhi)[10]) {
#pragma unroll
  for (int j = 0; j < 10; j++) {
    const int x = (j + ROT) % 10, tq = x < 8 ? x : 16 + x, tk = x < 8 ? 8 + x : 18 + x, tv = x < 8 ? 16 + x : 20 + x;
    khi[j] = pack2(acc[4 * tk + 2], acc[4 * tk + 3]);
    vhi[j] = movm(pack2(acc[4 * tv + 2], acc[4 * tv + 3]));
    qlo[j] = pack2(acc[4 * tq], acc[4 * tq + 1]);
    qhi[j] = pack2(acc[4 * tq + 2], acc[4 * tq + 3]);
    klo[j] = pack2(acc[4 * tk], acc[4 * tk + 1]);
    vlo[j] = pack2(acc[4 * tv], acc[4 * tv + 1]);
    asm volatile("" : "+r"(khi[j]), "+r"(qlo[j]), "+r"(qhi[j]), "+r"(klo[j]), "+r"(vlo[j]));
  }
}

template <int ROT> __device__ __forceinline__ void halo_send(const float* acc, uint4* ho, uint32_t tag) {
#pragma unroll
  for (int j = 0; j < 7; j++) {
    uint32_t x[3];
#pragma unroll
    for (int e = 0; e < 3; e++) {
      const int i = 3 * j + e, y = (i % 10 + ROT) % 10, tk = y < 8 ? 8 + y : 18 + y, tv = y < 8 ? 16 + y : 20 + y;
      x[e] = i < 10 ? pack2(acc[4 * tk + 2], acc[4 * tk + 3]) : i < 20 ? movm(pack2(acc[4 * tv + 2], acc[4 * tv + 3])) : 0u;
    }
    asm volatile("st.relaxed.gpu.global.v4.u32 [%0], {%1, %2, %3, %4};" ::"l"(ho + 32 * j), "r"(x[0]), "r"(x[1]), "r"(x[2]), "r"(tag) : "memory");
  }
}

__device__ __forceinline__ void attention(float* acc, uint32_t sb, int b, int par, int w, int lane, uint32_t tag, uint32_t zero) {
  const int g = lane >> 2, t = lane & 3;
  uint32_t klo[10], khi[10], vlo[10], vhi[10], qlo[10], qhi[10], kpv[10], vpv[10];
  if (HALO_FIRST && w == 3 && b < NCTA - 8) {
    uint4* ho = g_halo + (b * 2 + par) * 224 + lane;
    if (tail_first(b & 7)) halo_send<8>(acc, ho, tag);
    else halo_send<0>(acc, ho, tag);
    TSIF(par == 0, 76);
    pin<120>(acc);
  }
  if (tail_first(b & 7)) pack_qkv<8>(acc, qlo, qhi, klo, khi, vlo, vhi);
  else pack_qkv<0>(acc, qlo, qhi, klo, khi, vlo, vhi);
  const uint32_t xa = sb + OFF_KVX + (par * 3) * 2560 + lane * 16;
  if (w < 3) {
    sts128(xa + w * 2560, khi[0], khi[1], khi[2], khi[3]);
    sts128(xa + w * 2560 + 512, khi[4], khi[5], khi[6], khi[7]);
    sts128(xa + w * 2560 + 1024, khi[8], khi[9], vhi[0], vhi[1]);
    sts128(xa + w * 2560 + 1536, vhi[2], vhi[3], vhi[4], vhi[5]);
    sts128(xa + w * 2560 + 2048, vhi[6], vhi[7], vhi[8], vhi[9]);
  } else if (!HALO_FIRST && b < NCTA - 8) {
    uint4* ho = g_halo + (b * 2 + par) * 224 + lane;
#pragma unroll
    for (int j = 0; j < 7; j++) {
      const uint32_t x0 = j < 4 ? khi[3 * j] : vhi[3 * j - 10], x1 = j < 3 ? khi[3 * j + 1] : vhi[3 * j - 9];
      const uint32_t x2 = j < 3 ? khi[3 * j + 2] : j < 6 ? vhi[3 * j - 8] : 0u;
      asm volatile("st.relaxed.gpu.global.v4.u32 [%0], {%1, %2, %3, %4};" ::"l"(ho + 32 * j), "r"(x0), "r"(x1), "r"(x2), "r"(tag) : "memory");
    }
  }
  TSIF(par == 0 && w == 1, 64);
  TSIF(par == 0 && w == 3 && !HALO_FIRST, 76);
#pragma unroll
  for (int j = 0; j < 10; j++) vlo[j] = movm(vlo[j]);
  const bool far0 = 2 * t > g, far1 = 2 * t + 1 > g;
  const uint32_t mfar = (far0 ? 0x0000FFFFu : 0u) | (far1 ? 0xFFFF0000u : 0u);
  float slo[4][2], shi[4][2], lg[2][2];
  uint32_t phi[4], plo[4], qml[4], qmh[4];
#pragma unroll
  for (int h = 0; h < 4; h++) {
    const int f = h == 0 ? 0 : h == 1 ? 3 : h == 2 ? 5 : 8, hf = h < 2 ? 2 : 7;
    const bool mine = (h & 1) ? t >= 2 : t < 2;
    qml[h] = mine ? qlo[hf] : 0u;
    qmh[h] = mine ? qhi[hf] : 0u;
    float a[4] = {0.f, 0.f, 0.f, 0.f}, c[4] = {0.f, 0.f, 0.f, 0.f};
    mma16816(a, qlo[f], qhi[f], qlo[f + 1], qhi[f + 1], klo[f], klo[f + 1]);
    mma16816(c, qlo[f], qhi[f], qlo[f + 1], qhi[f + 1], khi[f], khi[f + 1]);
    mma1688(a, qml[h], qmh[h], klo[hf]);
    mma1688(c, qml[h], qmh[h], khi[hf]);
    slo[h][0] = a[0];
    slo[h][1] = a[1];
    shi[h][0] = lg[h & 1][0] = far0 ? a[2] : c[2];
    shi[h][1] = lg[h & 1][1] = far1 ? a[3] : c[3];
    if (!ATT_MERGE && (h & 1)) softmax_two(lg, phi[h - 1], phi[h]);
  }
  TSIF(par == 0 && w == 1, 65);
  if (ATT_GATE == 3 && lane == 0) mbar_arrive(sb + OFF_BAR + 8 * B_ATT2 + (phi[3] & zero));
  wg_sync(1 + par);
  TSIF(par == 0 && w == 1, 66);
  const bool nohist = (w == 0) && (b < 8);
  const uint4* hp = g_halo + ((b - 8) * 2 + par) * 224 + lane;
  uint32_t tg[7];
  if (w > 0) {
    const uint4 v0 = lds128(xa + (w - 1) * 2560), v1 = lds128(xa + (w - 1) * 2560 + 512), v2 = lds128(xa + (w - 1) * 2560 + 1024);
    const uint4 v3 = lds128(xa + (w - 1) * 2560 + 1536), v4 = lds128(xa + (w - 1) * 2560 + 2048);
    kpv[0] = v0.x; kpv[1] = v0.y; kpv[2] = v0.z; kpv[3] = v0.w; kpv[4] = v1.x; kpv[5] = v1.y; kpv[6] = v1.z; kpv[7] = v1.w;
    kpv[8] = v2.x; kpv[9] = v2.y; vpv[0] = v2.z; vpv[1] = v2.w; vpv[2] = v3.x; vpv[3] = v3.y; vpv[4] = v3.z; vpv[5] = v3.w;
    vpv[6] = v4.x; vpv[7] = v4.y; vpv[8] = v4.z; vpv[9] = v4.w;
  } else if (nohist) {
#pragma unroll
    for (int j = 0; j < 10; j++) kpv[j] = vpv[j] = 0u;
  } else {
    TSIF(par == 0, 77);
    halo_read(kpv, vpv, tg, hp);
  }
  if (w == 0 && !nohist) {
    int spins = 0;
    while (true) {
      bool ok = true;
#pragma unroll
      for (int j = 0; j < 7; j++) ok = ok && tg[j] == tag;
      if (__all_sync(0xffffffffu, ok) || ++spins > SPIN_LIMIT) break;
      halo_read(kpv, vpv, tg, hp);
    }
    TSIF(par == 0, 79);
  }
#pragma unroll
  for (int h = 0; h < 4; h++) {
    const int f = h == 0 ? 0 : h == 1 ? 3 : h == 2 ? 5 : 8, hf = h < 2 ? 2 : 7;
    float a[4] = {0.f, 0.f, 0.f, 0.f};
    mma16816(a, qlo[f], qhi[f], qlo[f + 1], qhi[f + 1], kpv[f], kpv[f + 1]);
    mma1688(a, qml[h], qmh[h], kpv[hf]);
    const float ninf = __int_as_float(0xff800000);
    lg[h & 1][0] = far0 ? (nohist ? ninf : a[0]) : slo[h][0];
    lg[h & 1][1] = far1 ? (nohist ? ninf : a[1]) : slo[h][1];
    if (h & 1) {
      softmax_two(lg, plo[h - 1], plo[h]);
      if (ATT_MERGE) {
        const float lh[2][2] = {{shi[h - 1][0], shi[h - 1][1]}, {shi[h][0], shi[h][1]}};
        softmax_two(lh, phi[h - 1], phi[h]);
      }
    }
  }
  TSIF(par == 0 && w <= 1, 67 + w);
  if (ATT_GATE == 2 && lane == 0) mbar_arrive(sb + OFF_BAR + 8 * B_ATT2 + (plo[3] & zero));
  uint32_t ov[20];
#pragma unroll
  for (int hp = 0; hp < 2; hp++) {
    const int hf = hp ? 7 : 2;
    float sh[4] = {0.f, 0.f, 0.f, 0.f}, i0 = 0.f, i1 = 0.f;
#pragma unroll
    for (int e = 0; e < 2; e++) {
      const int h = 2 * hp + e, f = h == 0 ? 0 : h == 1 ? 3 : h == 2 ? 5 : 8;
      const uint32_t a0 = plo[h] & mfar, a2 = plo[h] & ~mfar, a3 = phi[h] & mfar, c1 = phi[h] & ~mfar;
      float sum[4] = {0.f, 0.f, 0.f, 0.f};
      mma1688(sum, plo[h], phi[h], 0x3F803F80u);
      const float r0 = rcp(sum[0]), r1 = rcp(sum[2]);
#pragma unroll
      for (int j = f; j < f + 2; j++) {
        float o[4] = {0.f, 0.f, 0.f, 0.f};
        mma16816(o, a0, 0u, a2, a3, vpv[j], vlo[j]);
        mma1688(o, 0u, c1, vhi[j]);
        ov[2 * j] = pack2(o[0] * r0, o[1] * r0);
        ov[2 * j + 1] = pack2(o[2] * r1, o[3] * r1);
      }
      const bool mine = e ? g >= 4 : g < 4;
      mma16816(sh, a0, 0u, a2, a3, mine ? vpv[hf] : 0u, mine ? vlo[hf] : 0u);
      mma1688(sh, 0u, c1, mine ? vhi[hf] : 0u);
      if (e == 0 || t >= 2) {
        i0 = r0;
        i1 = r1;
      }
    }
    ov[2 * hf] = pack2(sh[0] * i0, sh[1] * i0);
    ov[2 * hf + 1] = pack2(sh[2] * i1, sh[3] * i1);
  }
  if (ATT_GATE == 4 && lane == 0) mbar_arrive(sb + OFF_BAR + 8 * B_ATT2 + (ov[19] & zero));
  TS(32 + 4 * par + w);
  mbar_wait(sb + OFF_BAR + 8 * B_P1, 0);
  const uint32_t oa = sb + OFF_OA + (lane >> 4) * 2048 + (32 * w + 2 * (lane & 15) + par) * 16;
#pragma unroll
  for (int j = 0; j < 5; j++) stsm4(oa + 4096 * j, ov + 4 * j);
  TSIF(par == 0 && w == 0, 120);
  fence_async_smem();
  TSIF(par == 0 && w == 0, 121);
  __syncwarp();
  if (lane == 0) mbar_arrive(sb + OFF_BAR + 8 * B_ATTN);
  TSM(w == 0 || w == 2, 122 + par + (w == 2 ? 3 : 0));
}

struct Maps {
  CUtensorMap x, wm, wt, k, v, y, wo, qm, qt, om, ot, u;
};

__device__ __forceinline__ void load_stage(uint32_t sb, int kb, int b, const Maps& m) {
  const uint32_t st = sb + (kb & 3) * STAGE_BYTES, bar = sb + OFF_BAR + 8 * (B_FULL1 + (kb & 3));
  const int r = b >> 3, hg = b & 7, slab = kb - KV_KB;
  const bool kv = slab >= 0 && slab < 5;
  const uint32_t kbar = sb + OFF_BAR + 8 * (B_KV + slab), dst = sb + OFF_KVS + slab * KVS_BYTES;
  mbar_expect_tx(bar, STAGE_BYTES);
  if (kv) mbar_expect_tx(kbar, KVS_BYTES);
  tma_3d(st, &m.x, 64 * kb, 64 * r, 0, bar);
  if (kv && KV_MIX) tma_3d(dst, &m.k, 0, 32 * (b >> 1) - 3, 2 * slab + (b & 1), kbar);
  tma_3d(st + ST_W, &m.wm, 80 * hg + (tail_first(hg) ? 16 : 0), 64 * kb, 0, bar);
  if (kv && KV_MIX) tma_3d(dst + KVS_V, &m.v, 0, 32 * (b >> 1), 2 * slab + (b & 1), kbar);
  tma_3d(st + ST_WT, &m.wt, 80 * hg + (tail_first(hg) ? 0 : 64), 64 * kb, 0, bar);
  if (kv && !KV_MIX) tma_3d(dst, &m.k, 0, 32 * (b >> 1) - 3, 2 * slab + (b & 1), kbar);
  if (kv && !KV_MIX) tma_3d(dst + KVS_V, &m.v, 0, 32 * (b >> 1), 2 * slab + (b & 1), kbar);
}

__global__ void __launch_bounds__(NTHR, 1) fused_kernel(const __grid_constant__ Maps m, const Params p) {
  extern __shared__ __align__(1024) uint8_t smem[];
  const uint32_t sb = (uint32_t)__cvta_generic_to_shared(smem);
  const uint32_t bars = sb + OFF_BAR;
  const int tid = threadIdx.x, lane = tid & 31;
  int b = blockIdx.x;
  if (BMAP == 1) b = (((b & 63) >> 3) * 2 + (b & 1)) * 8 + (((b < 64 ? 0x6521 : 0x7430) >> (4 * ((b >> 1) & 3))) & 7);
  if (BMAP == 2) b = ((b & 63) >> 2) * 8 + (((b < 64 ? 0x6521 : 0x7430) >> (4 * (b & 3))) & 7);
  if (BMAP == 3) b = (((b & 63) >> 3) * 2 + (b & 1)) * 8 + (((b < 64 ? 0x7430 : 0x6521) >> (4 * ((b >> 1) & 3))) & 7);
  if (BMAP == 4) b = (((b >> 4) * 2 + (b & 1)) * 8) + ((b >> 1) & 7);
  if (BMAP == 5) b = 127 - b;
  const int r = b >> 3, hg = b & 7;

  if (tid == T_ISSUE) {
    TSM(true, 0);
#pragma unroll
    for (int i = 0; i < 4; i++) mbar_init(bars + 8 * (B_FULL1 + i), 1);
#pragma unroll
    for (int i = 0; i < 3; i++) mbar_init(bars + 8 * (B_KV + i), 1);
    fence_async_smem();
#pragma unroll 1
    for (int kb = 0; kb <= PRE2; kb++) load_stage(sb, kb, b, m);
  } else if (tid >= T_PF && tid < T_PF + 12) {
    tm_prefetch(&m.x + (tid - T_PF));
  } else if (tid == T_INIT) {
#pragma unroll
    for (int i = 0; i < 4; i++) mbar_init(bars + 8 * (B_EMPTY1 + i), 8);
#pragma unroll
    for (int i = 0; i < 8; i++) mbar_init(bars + 8 * (B_FULL2 + i), 1);
#pragma unroll
    for (int i = 0; i < 4; i++) mbar_init(bars + 8 * (B_EMPTY2 + i), 8);
#pragma unroll
    for (int i = 0; i < 4; i++) mbar_init(bars + 8 * (B_U + i), 1);
    mbar_init(bars + 8 * B_HA, 4);
    mbar_init(bars + 8 * B_GATE, 4);
    mbar_init(bars + 8 * B_HB, 1);
    mbar_init(bars + 8 * B_KVD, 4);
    mbar_init(bars + 8 * B_QF, 1);
    mbar_init(bars + 8 * B_ATTN, 8);
    mbar_init(bars + 8 * B_ATT2, 8);
    mbar_init(bars + 8 * B_P1, 8);
    mbar_init(bars + 8 * B_C34, 1);
    mbar_init(bars + 8 * B_YRB, 1);
#pragma unroll
    for (int i = 0; i < 5; i++) mbar_init(bars + 8 * (B_YST + i), 4);
#pragma unroll
    for (int i = 0; i < 5; i++) mbar_init(bars + 8 * (B_US + i), U_TMA ? 4 : i == 2 ? 20 : 1);
    mbar_init(bars + 8 * B_YSIG, 1);
    mbar_init(bars + 8 * B_YFULL, 1);
    mbar_init(bars + 8 * B_EPOCH, 1);
    mbar_init(bars + 8 * B_PREP, 4);
    mbar_init(bars + 8 * B_USIG, 1);
    mbar_init(bars + 8 * B_WST, 1);
#pragma unroll
    for (int i = 3; i < 5; i++) mbar_init(bars + 8 * (B_KV + i), 1);
    mbar_init(bars + 8 * B_E3, 8);
    mbar_init(bars + 8 * B_LAST, 1);
    mbar_init(bars + 8 * B_OSIG, 1);
    mbar_init(bars + 8 * B_WOP, 1);
    fence_async_smem();
  }
  const int warp = __shfl_sync(0xffffffffu, tid >> 5, 0), wg = warp >> 2, w = warp & 3;
  __syncthreads();

  if (wg == 3) {
    asm volatile("setmaxnreg.dec.sync.aligned.u32 56;");
    if (w == 0) {
      if (lane == 0) {
#pragma unroll 1
        for (int kb = 1 + PRE2; kb < 10; kb++) {
          if (kb >= 4) mbar_wait(bars + 8 * (kb == 7 ? B_E3 : B_EMPTY1 + (kb & 3)), (kb >> 3) & 1);
          TSIF(kb >= 4, 44 + kb);
          load_stage(sb, kb, b, m);
          TSIF(kb == 3, 60);
          if (kb == TRIG_KB) mbar_arrive(bars + 8 * B_LAST);
        }
        mbar_wait(bars + 8 * B_WOP, 0);
        mbar_wait(bars + 8 * WL_TRIG, 0);
        mbar_wait(bars + 8 * B_EPOCH, 0);
        flag_wait(g_cnt + C_W + 32 * hg, (lds32(sb + OFF_EPOCH) + 1) * 16);
        TS(30);
#pragma unroll 1
        for (int j = 0; j < 8; j++) {
          if (j >= 6) mbar_wait(bars + 8 * (B_EMPTY2 + j - 6), 0);
          if (j == 4) mbar_wait(bars + 8 * B_ATTN, 0);
          TSIF(j >= 6, 100 + j);
          if (RF_GATE && j == 6) mbar_wait(bars + 8 * B_YSIG, 0);
          mbar_expect_tx(bars + 8 * (B_FULL2 + j), j == 0 ? WO_BYTES : j == 5 ? O_BYTES + WO_BYTES + 512 : O_BYTES + WO_BYTES);
          bulk_load(sb + off_w(j), g_WO + (hg * 8 + step_src(hg, j)) * 800, WO_BYTES, bars + 8 * (B_FULL2 + j));
        }
        mbar_wait(bars + 8 * (B_EMPTY2 + Q_SLOT), 0);
        mbar_expect_tx(bars + 8 * B_QF, O_BYTES);
        tma_2d(sb + OFF_QS, &m.qm, 80 * hg, 128 * r, bars + 8 * B_QF);
        if (!QBOX) tma_2d(sb + OFF_QT, &m.qt, 80 * hg + 64, 128 * r, bars + 8 * B_QF);
      }
    } else if (w == 1) {
      unsigned epoch = 0;
      if (lane == 0) {
        epoch = atomicAdd(g_cnt + C_LAUNCH, 1u) / NCTA;
        asm volatile("st.shared.u32 [%0], %1;" ::"r"(sb + OFF_EPOCH), "r"(epoch) : "memory");
        mbar_arrive(bars + 8 * B_EPOCH);
        mbar_wait(bars + 8 * B_KVD, 0);
        mbar_expect_tx(bars + 8 * B_HB, 5 * 4096);
#pragma unroll 1
        for (int c = 0; c < 5; c++) {
          if (c == 3) mbar_wait(bars + 8 * B_S3, 0);
          bulk_load(sb + off_ch(c) + U_BYTES, p.ssm_k + (5 * b + c) * SEQ, 4096, bars + 8 * B_HB);
        }
#pragma unroll
        for (int c = 0; c < 4; c++) mbar_expect_tx(bars + 8 * (B_U + c), c < 3 ? U_BYTES : 2 * U_BYTES);
        const uint4* usrc = g_U + 5 * b * U_PITCH;
        mbar_wait(bars + 8 * B_USIG, 0);
        flag_wait(g_cnt + C_PREP + 32 * (b & 15), (epoch + 1) * NCTA);
        TS(23);
#pragma unroll
        for (int c = 0; c < 5; c++) {
          if (c == 3 && U_TRIM) mbar_wait(bars + 8 * (B_U + 2), 0);
          bulk_load(sb + off_ch(c), usrc + c * U_PITCH, U_BYTES, bars + 8 * (B_U + (c < 3 ? c : 3)));
          TSIF(c == 0 || c == 4, 116 + (c >> 2));
        }
      }
      epoch = __shfl_sync(0xffffffffu, epoch, 0);
      if (lane < 8) {
        const int src = (b & ~7) | step_src(hg, lane);
        mbar_wait(bars + 8 * OP_TRIG, 0);
        TS(20);
        bool seen = false;
#pragma unroll 1
        for (int spins = 0; spins < SPIN_LIMIT; spins++) {
          const bool now = !seen && (int)(flag_read(g_cnt + C_O + 32 * src) - (epoch + 1)) >= 0;
          if (now && lane >= 1 && lane < 4) bulk_load(sb + off_o(lane), g_O + src * 1280, O_BYTES, bars + 8 * (B_FULL2 + lane));
          seen = seen || now;
          if (__all_sync(0xff, seen)) break;
        }
        TS(21);
        if (lane == 5) bulk_load(sb + OFF_GATE, g_gate + 128 * r, 512, bars + 8 * (B_FULL2 + 5));
#pragma unroll 1
        for (int j = 4; j < 8; j++) {
          if (lane == j) {
            mbar_wait(bars + 8 * (j < 6 ? B_C34 : B_EMPTY2 + j - 6), 0);
            if (RF_GATE && j == 6) mbar_wait(bars + 8 * B_YSIG, 0);
            bulk_load(sb + off_o(j), g_O + src * 1280, O_BYTES, bars + 8 * (B_FULL2 + j));
          }
          __syncwarp(0xff);
        }
        TS(22);
      }
    } else if (w == 2) {
      mbar_wait(bars + 8 * B_PREP, 0);
      flag_signal(g_cnt + C_PREP, 16, lane);
      TS(25);
      if (lane == 0) mbar_arrive(bars + 8 * B_USIG);
      mbar_wait(bars + 8 * B_GATE, 0);
      if (G_TMA) {
        if (lane == 0) {
          asm volatile("cp.async.bulk.global.shared::cta.bulk_group [%0], [%1], 64;\ncp.async.bulk.commit_group;\n"
                       "cp.async.bulk.wait_group.read 0;" ::"l"(g_gate + 16 * b), "r"(sb + OFF_GATE + 64 * hg) : "memory");
          bulk_load(sb + OFF_GATE + 64 * hg, g_gate + 16 * b, 64, bars + 8 * B_ORB);
        }
      } else if (((NOMB & 1) || O_RB) && lane == 0) {
        asm volatile("fence.release.gpu;" ::: "memory");
      }
      mbar_wait(bars + 8 * B_ATTN, 0);
      if (lane == 0) {
        if (O_DEFER) mbar_wait(bars + 8 * (B_U + 3), 0);
        asm volatile("cp.async.bulk.global.shared::cta.bulk_group [%0], [%1], 20480;\ncp.async.bulk.commit_group;"
                     ::"l"(g_O + b * 1280), "r"(sb + OFF_OA) : "memory");
        if (O_RB == 2) {
          asm volatile("cp.async.bulk.wait_group.read 0;" ::: "memory");
          mbar_expect_tx(bars + 8 * B_ORB, O_BYTES + 64 * G_TMA);
          bulk_load(sb + OFF_OA, g_O + b * 1280, O_BYTES, bars + 8 * B_ORB);
          mbar_wait(bars + 8 * B_ORB, 0);
          flag_bump(g_cnt + C_O + 32 * b);
        } else if (O_RB) asm volatile("cp.async.bulk.wait_group.read 0;" ::: "memory");
        else asm volatile("cp.async.bulk.wait_group 0;\nfence.proxy.async.global;" ::: "memory");
      }
      TS(74);
      if (O_RB == 2) {
      } else if (O_RB) {
        __syncwarp();
        unsigned v[5];
#pragma unroll
        for (int c = 0; c < 5; c++) v[c] = flag_read(reinterpret_cast<const unsigned*>(g_O + b * 1280 + 256 * c + 8 * lane + 7));
        const unsigned dep = __reduce_or_sync(0xffffffffu, (v[0] ^ v[1] ^ v[2] ^ v[3] ^ v[4]) & p.zero);
        if (lane == 0) flag_bump(g_cnt + C_O + 32 * b + dep);
      } else if (!(NOMB & 1)) flag_signal(g_cnt + C_O + 32 * b, 1, lane);
      else if (lane == 0) flag_bump(g_cnt + C_O + 32 * b);
      TS(26);
      if (lane == 0) mbar_arrive(bars + 8 * B_OSIG);

    } else {
      if (lane == 0) {
        uint4* dst = g_WO + (hg * 8 + (r >> 1)) * 800 + (r & 1) * 80;
        if (WPF) {
          mbar_wait(bars + 8 * WPF, 0);
          if (WPF_LIN)
            asm volatile("cp.async.bulk.prefetch.L2.global [%0], 6400;" ::"l"(p.wo + b * 3200) : "memory");
          else
            asm volatile("cp.async.bulk.prefetch.tensor.3d.L2.global [%0, {%1, %2, %3}];" ::"l"(&m.wo), "r"(0), "r"(40 * r), "r"(5 * hg) : "memory");
        }
        mbar_wait(bars + 8 * B_P1, 0);
        mbar_wait(bars + 8 * WB_TRIG, 0);
        mbar_expect_tx(bars + 8 * B_WST, WO_BYTES / 2);
        tma_3d(sb + OFF_WS, &m.wo, 0, 40 * r, 5 * hg, bars + 8 * B_WST);
        mbar_wait(bars + 8 * B_WST, 0);
        mbar_wait(bars + 8 * WO_TRIG, 0);
#pragma unroll 1
        for (int n = 0; n < 5; n++)
          asm volatile("cp.async.bulk.global.shared::cta.bulk_group [%0], [%1], 1280;" ::"l"(dst + 160 * n), "r"(sb + OFF_WS + 1280 * n) : "memory");
        if (W_RB) {
          asm volatile("cp.async.bulk.commit_group;\ncp.async.bulk.wait_group.read 0;" ::: "memory");
          mbar_expect_tx(bars + 8 * B_WST, WO_BYTES / 2);
#pragma unroll 1
          for (int n = 0; n < 5; n++) bulk_load(sb + OFF_WS + 1280 * n, dst + 160 * n, 1280, bars + 8 * B_WST);
          mbar_wait(bars + 8 * B_WST, 1);
        } else {
          asm volatile("cp.async.bulk.commit_group;\ncp.async.bulk.wait_group 0;\nfence.proxy.async.global;" ::: "memory");
          if (!(NOMB & 4)) asm volatile("fence.release.gpu;" ::: "memory");
        }
        flag_bump(g_cnt + C_W + 32 * hg);
        mbar_arrive(bars + 8 * B_WOP);
        TS(71);
        mbar_expect_tx(bars + 8 * B_C34, 3 * U_BYTES);
        mbar_expect_tx(bars + 8 * B_YRB, 2 * U_BYTES);
#pragma unroll 1
        for (int c = 0; c < 5; c++) {
          mbar_wait(bars + 8 * (B_YST + c), 0);
          asm volatile("cp.async.bulk.global.shared::cta.bulk_group [%0], [%1], 4096;\ncp.async.bulk.commit_group;\n"
                       "cp.async.bulk.wait_group.read 0;" ::"l"(g_Y + (5 * b + c) * Y_PITCH), "r"(sb + off_ch(c)) : "memory");
          bulk_load(sb + off_ch(c), g_Y + (5 * b + c) * Y_PITCH, U_BYTES, bars + 8 * (c < 3 ? B_C34 : B_YRB));
        }
        TS(75);
        mbar_wait(bars + 8 * B_C34, 0);
        mbar_wait(bars + 8 * B_YRB, 0);
        flag_bump(g_cnt + C_Y + 32 * (b >> 4));
        TS(27);
        mbar_arrive(bars + 8 * B_YSIG);
        mbar_expect_tx(bars + 8 * B_YFULL, 20480);
        flag_wait(g_cnt + C_Y + 32 * hg, (lds32(sb + OFF_EPOCH) + 1) * 16);
        TS(24);
        tma_2d(sb + OFF_YT, &m.y, 128 * r, 80 * hg, bars + 8 * B_YFULL);
        tma_2d(sb + OFF_YT + 10240, &m.y, 128 * r + 64, 80 * hg, bars + 8 * B_YFULL);
      }
    }
  } else {
    asm volatile("setmaxnreg.inc.sync.aligned.u32 152;");
    if (wg < 2) {
      float acc[120];
#pragma unroll
      for (int i = 0; i < 120; i++) acc[i] = 0.f;
      const uint32_t da = desc_lo(sb + wg * 8192, 16), db = desc_lo(sb + ST_W, 8192), dc = desc_lo(sb + ST_WT, 2048);
      if (PW1) pin<120>(acc);
      if (PW1 == 2) mbar_wait(bars + 8 * B_FULL1, 0);
#pragma unroll 1
      for (int kb = 0; kb < 10; kb++) {
        mbar_wait(bars + 8 * (B_FULL1 + (kb & 3)), (kb >> 2) & 1);
        const uint32_t so = (kb & 3) * (STAGE_BYTES >> 4);
        wg_fence();
#pragma unroll
        for (int k = 0; k < 4; k++) {
          WgSST<192>::mma<HI_SW128, HI_SW128>(acc, da + so + 2 * k, db + so + 128 * k, 1);
          WgSST<48>::mma<HI_SW128, HI_SW32>(acc + 96, da + so + 2 * k, dc + so + 32 * k, 1);
        }
        wg_commit();
        wg_wait<1>();
        if (kb > 0 && lane == 0) mbar_arrive(bars + 8 * (kb == 4 ? B_E3 : B_EMPTY1 + ((kb - 1) & 3)));
      }
      mbar_wait(bars + 8 * B_EPOCH, 0);
      const uint32_t tag = lds32(sb + OFF_EPOCH) + 1;
      mbar_wait(bars + 8 * B_S3, 0);
      wg_wait<0>();
      pin<120>(acc);
      if (lane == 0) mbar_arrive(bars + 8 * B_P1);
      TSM(w == 0, 3 + wg);
      attention(acc, sb, b, wg, w, lane, tag, p.zero);
    } else {
      const int tw = tid & 127, chl = 64 * (b & 1) + 8 * w + (lane >> 2);
      uint4* up = g_U + chl * U_PITCH + ((4 * (b >> 1) + (lane & 3)) ^ ((b >> 2) & 1));
      uint2 sw[10];
      uint32_t dv = 0;
      if (lane < 5) dv = __ldg(reinterpret_cast<const unsigned short*>(p.ssm_D) + 5 * b + lane);
#pragma unroll
      for (int i = 0; i < 10; i++) sw[i] = ldg64(reinterpret_cast<const uint2*>(p.shift_k) + chl + 128 * (i >> 1) + 32 * (i & 1));
      uint32_t tab[12];
      uint32_t tt[2];
      fft_tables(tab, tw);
      fft_twiddles(tt, tw);
      uint4 res[10];
#pragma unroll
      for (int i = 0; i < 10; i++) res[i] = make_uint4(0, 0, 0, 0);
#pragma unroll 1
      for (int slab = 0; slab < 5; slab++) {
#pragma unroll
        for (int i = 0; i < 8; i++) res[i] = res[i + 2];
        prep_slab(res + 8, sw, sb, slab, w, lane);
        TSIF(w == 0, 99 + 4 * slab);
#pragma unroll
        for (int i = 0; i < 8; i++) sw[i] = sw[i + 2];
      }
      TSIF(w == 0, 28);
      __syncwarp();
      if (lane == 0) mbar_arrive(bars + 8 * B_KVD + ((res[8].x ^ res[9].x) & p.zero));
      mbar_wait(bars + 8 * B_KVD, 0);
      fft_tables_store(tab, sb, tw);
      mbar_wait(bars + 8 * B_LAST, 0);
#pragma unroll
      for (int i = 0; i < 10; i++) up[(128 * (i >> 1) + 32 * (i & 1)) * U_PITCH] = res[i];
      __syncwarp();
      if (lane == 0) mbar_arrive(bars + 8 * B_PREP);
      TSIF(w == 0 && !U_TMA, 5);
      mbar_wait(bars + 8 * (G_AFTER ? B_USIG : B_LAST), 0);
      prep_gate(p, sb, b, w, lane);
      __syncwarp();
      if (lane == 0) mbar_arrive(bars + 8 * B_GATE);
      TSIF(w == 0, 72);
      mbar_wait(bars + 8 * B_HB, 0);
      TSIF(w == 0, 2);
      const uint32_t ha = sb + U_BYTES + ((tw >> 3) * 16 + 8 + (tw & 7)) * 16;
      uint4 hv[5];
#pragma unroll
      for (int c = 0; c < 5; c++) hv[c] = lds128(ha + off_ch(c));
      __syncwarp();
#pragma unroll
      for (int c = 0; c < 5; c++) sts128((ha ^ 16) + off_ch(c), hv[c].x, hv[c].y, hv[c].z, hv[c].w);
      asm volatile("st.shared.v2.u32 [%0], {%1, %2};" ::"r"(sb + OFF_TT + 8 * tw), "r"(tt[0]), "r"(tt[1]) : "memory");
      if (tw < 5) asm volatile("st.shared.f32 [%0], %1;" ::"r"(sb + OFF_D + 4 * tw), "f"(bf_lo(dv) * 0.125f) : "memory");
      fence_async_smem();
      __syncwarp();
      if (lane == 0) mbar_arrive(bars + 8 * B_HA);
      TSIF(w == 0, 6);
    }

    FftConst fc;
    TSM(w == 0 && wg == 0, 104);
    mbar_wait(bars + 8 * B_HA, 0);
    fft_matrices(fc, sb, w, lane);
    TSM(w == 0 && wg == 0, 105);
    TSM(w == 0 && wg == 2, 124);
    uint32_t tasks = wg == 0 ? TASK0 : wg == 1 ? TASK1 : TASK2, fa[4][4];
    {
      float X[32];
      wg_fence();
      f_step(X, fc, desc_lo(sb + off_ch((tasks & 7) - 1) + U_BYTES, 1024));
      wg_wait<0>();
      pin<32>(X);
      twiddle_fwd(fa, X, fc);
    }
#pragma unroll 1
    for (; tasks; tasks >>= 4) {
      const int c = (tasks & 7) - 1;
      conv_channel(fc, fa, sb, c, ((tasks >> 4) & 7) - 1, wg, w, lane);
      if (lane == 0) mbar_arrive(bars + 8 * (B_YST + c));
      TSM(w == 0, 10 + c);
    }

    if (wg < 2) {
      const int g = lane >> 2;
      float acc[40];
#pragma unroll
      for (int i = 0; i < 40; i++) acc[i] = 0.f;
      const uint32_t da = desc_lo(sb + wg * 1024, 2048), db = desc_lo(sb, 2560);
      mbar_wait(bars + 8 * (O_RB == 2 ? B_ORB : B_ATTN), 0);
      if (PW2) mbar_wait(bars + 8 * B_FULL2, 0);
      mbar_wait(bars + 8 * B_CVD, 0);
      TSM(w == 0, 15 + wg);
#pragma unroll 1
      for (int j = 0; j < 8; j++) {
        mbar_wait(bars + 8 * (B_FULL2 + j), 0);
        TSM(w == 0 && wg == 0, 44 + (j < 4 ? j : j + 6));
        const uint32_t oa = da + (off_o(j) >> 4), ob = db + (off_w(j) >> 4);
        wg_fence();
#pragma unroll
        for (int k = 0; k < 5; k++) WgSST<80>::mma<HI_NONE, HI_SW32>(acc, oa + 256 * k, ob + 32 * k, 1);
        wg_commit();
        wg_wait<1>();
        if (j >= 1 && j <= Q_SLOT + 1 && lane == 0) mbar_arrive(bars + 8 * (B_EMPTY2 + j - 1));
      }
      TSIF(w == 0 && wg == 0, 113);
      const int tr = 64 * wg + 16 * w + (lane & 15);
      const uint32_t fm = sb + OFF_QS + tr * 128, fx = (lane >> 4) ^ (tr & 7), fq = sb + OFF_QS + tr * 160 + (lane >> 4) * 16;
      const uint32_t ft = sb + OFF_QT + tr * 32 + (((lane >> 4) ^ (tr >> 2)) & 1) * 16;
      const float g0 = __uint_as_float(lds32(sb + OFF_GATE + (64 * wg + 16 * w + g) * 4));
      const float g1 = __uint_as_float(lds32(sb + OFF_GATE + (64 * wg + 16 * w + 8 + g) * 4));
      const uint32_t ga = pack2(g0, g0), gb = pack2(g1, g1);
      const uint32_t na = pack2(1.f - g0, 1.f - g0), nb = pack2(1.f - g1, 1.f - g1);

      uint32_t qf[20];
      mbar_wait(bars + 8 * B_QF, 0);
      TSM(w == 0 && wg == 0, 99);
#pragma unroll
      for (int j = 0; j < 5; j++) ldsm4(qf + 4 * j, QBOX ? fq + 32 * j : j < 4 ? fm + ((fx ^ (2 * j)) << 4) : ft);
      if (FUSE_MIX) {
#pragma unroll
        for (int i = 0; i < 20; i++) {
          qf[i] = bmul((i & 1) ? gb : ga, qf[i]);
          asm volatile("" : "+r"(qf[i]));
        }
      }
      wg_wait<0>();
      pin<40>(acc);
      TSM(w == 0, 17 + wg);
      uint32_t pb[20];
#pragma unroll
      for (int j = 0; j < 10; j++) {
        pb[2 * j] = bmul(na, pack2(acc[4 * j], acc[4 * j + 1]));
        pb[2 * j + 1] = bmul(nb, pack2(acc[4 * j + 2], acc[4 * j + 3]));
        asm volatile("" : "+r"(pb[2 * j]), "+r"(pb[2 * j + 1]));
      }
      const uint32_t ya = sb + OFF_YT + wg * 10240 + ((lane >> 4) * 8 + (lane & 7)) * 128 +
                          (((2 * w + (((lane >> 3) & 1) ^ wg)) ^ (lane & 7)) << 4);
      mbar_wait(bars + 8 * B_YFULL, 0);
      TSM(w == 0 && wg == 0, 19);
#pragma unroll
      for (int j = 0; j < 5; j++) {
        uint32_t y[4];
        ldsm4t(y, ya + 2048 * j);
#pragma unroll
        for (int i = 0; i < 4; i++)
          qf[4 * j + i] = FUSE_MIX ? bfma(qf[4 * j + i], y[i], pb[4 * j + i]) : badd(bmul((i & 1) ? gb : ga, bmul(qf[4 * j + i], y[i])), pb[4 * j + i]);
      }
#pragma unroll
      for (int j = 0; j < 5; j++) stsm4(QBOX ? fq + 32 * j : j < 4 ? fm + ((fx ^ (2 * j)) << 4) : ft, qf + 4 * j);
      fence_async_smem();
      __syncwarp();
      if (lane == 0) {
        const int row = 64 * wg + 16 * w;
        asm volatile("cp.async.bulk.tensor.2d.global.shared::cta.bulk_group [%0, {%2, %3}], [%1];"
                     ::"l"(&m.om), "r"(sb + OFF_QS + row * (QBOX ? 160 : 128)), "r"(80 * hg), "r"(128 * r + row) : "memory");
        if (!QBOX) asm volatile("cp.async.bulk.tensor.2d.global.shared::cta.bulk_group [%0, {%2, %3}], [%1];"
                     ::"l"(&m.ot), "r"(sb + OFF_QT + row * 32), "r"(80 * hg + 64), "r"(128 * r + row) : "memory");
        asm volatile("cp.async.bulk.commit_group;\ncp.async.bulk.wait_group.read 0;" ::: "memory");
      }
      TSM(w == 0 || w == 3, 40 + 2 * wg + (w & 1));
      if (ENDBAR) asm volatile("bar.sync 15, 256;" ::: "memory");
    }
  }
}

typedef CUresult (*EncodeFn)(CUtensorMap*, CUtensorMapDataType, cuuint32_t, void*, const cuuint64_t*, const cuuint64_t*,
                             const cuuint32_t*, const cuuint32_t*, CUtensorMapInterleave, CUtensorMapSwizzle,
                             CUtensorMapL2promotion, CUtensorMapFloatOOBfill);

void encode(EncodeFn fn, CUtensorMap* tm, const void* base, int rank, const cuuint64_t* dims, const cuuint64_t* strides,
            const cuuint32_t* box, CUtensorMapSwizzle swz) {
  const cuuint32_t ones[3] = {1, 1, 1};
  fn(tm, CU_TENSOR_MAP_DATA_TYPE_BFLOAT16, rank, const_cast<void*>(base), dims, strides, box, ones,
     CU_TENSOR_MAP_INTERLEAVE_NONE, swz, CU_TENSOR_MAP_L2_PROMOTION_L2_128B, CU_TENSOR_MAP_FLOAT_OOB_FILL_NONE);
}

}

extern "C" void kernel_launch(void* const* d_in, const int* in_sizes, int n_in, void* d_out, int out_size) {
  (void)in_sizes; (void)n_in; (void)out_size;
  Params p;
  p.q = (const __nv_bfloat16*)d_in[0];
  p.k = (const __nv_bfloat16*)d_in[1];
  p.v = (const __nv_bfloat16*)d_in[2];
  p.shift_k = (const __nv_bfloat16*)d_in[3];
  p.ssm_k = (const __nv_bfloat16*)d_in[4];
  p.ssm_D = (const __nv_bfloat16*)d_in[5];
  p.wqkv = (const __nv_bfloat16*)d_in[7];
  p.wo = (const __nv_bfloat16*)d_in[8];
  p.gate_w = (const __nv_bfloat16*)d_in[9];
  p.out = (__nv_bfloat16*)d_out;
  p.zero = 0;

  static EncodeFn fn = nullptr;
  static void *yaddr = nullptr, *uaddr = nullptr;
  if (!fn) {
    cudaDriverEntryPointQueryResult qr;
    void* f = nullptr;
    cudaGetDriverEntryPoint("cuTensorMapEncodeTiled", &f, cudaEnableDefault, &qr);
    fn = (EncodeFn)f;
    cudaGetSymbolAddress(&yaddr, g_Y);
    cudaGetSymbolAddress(&uaddr, g_U);
    cudaFuncSetAttribute(fused_kernel, cudaFuncAttributeMaxDynamicSharedMemorySize, SMEM_BYTES);
  }
  Maps m;
  {
    const cuuint64_t dims[3] = {640, 1024, 2}, st[2] = {2560, 1280};
    const cuuint32_t box[3] = {64, 64, 2};
    encode(fn, &m.x, p.q, 3, dims, st, box, CU_TENSOR_MAP_SWIZZLE_128B);
  }
  {
    const cuuint64_t dims[3] = {640, 640, 3}, st[2] = {3840, 1280};
    const cuuint32_t box[3] = {64, 64, 3}, boxt[3] = {16, 64, 3};
    encode(fn, &m.wm, p.wqkv, 3, dims, st, box, CU_TENSOR_MAP_SWIZZLE_128B);
    encode(fn, &m.wt, p.wqkv, 3, dims, st, boxt, CU_TENSOR_MAP_SWIZZLE_32B);
  }
  {
    const cuuint64_t dims[3] = {64, 2048, 10}, st[2] = {1280, 128};
    const cuuint32_t boxk[3] = {64, 35, 1}, boxv[3] = {64, 32, 1};
    encode(fn, &m.k, p.k, 3, dims, st, boxk, CU_TENSOR_MAP_SWIZZLE_128B);
    encode(fn, &m.v, p.v, 3, dims, st, boxv, CU_TENSOR_MAP_SWIZZLE_128B);
  }
  {
    const cuuint64_t dims[3] = {16, 640, 40}, st[2] = {1280, 32};
    const cuuint32_t box[3] = {16, 40, 5};
    encode(fn, &m.wo, p.wo, 3, dims, st, box, CU_TENSOR_MAP_SWIZZLE_32B);
  }
  {
    const cuuint64_t dims[2] = {2048, 640}, st[1] = {Y_PITCH * 16};
    const cuuint32_t box[2] = {64, 80};
    encode(fn, &m.y, yaddr, 2, dims, st, box, CU_TENSOR_MAP_SWIZZLE_128B);
    const cuuint64_t stu[1] = {U_PITCH * 16};
    const cuuint32_t boxu[2] = {32, 64};
    encode(fn, &m.u, uaddr, 2, dims, stu, boxu, CU_TENSOR_MAP_SWIZZLE_NONE);
  }
  {
    const cuuint64_t dims[2] = {640, 2048}, st[1] = {1280};
    const cuuint32_t bqm[2] = {QBOX ? 80 : 64, 128}, bqt[2] = {16, 128}, bom[2] = {QBOX ? 80 : 64, 16}, bot[2] = {16, 16};
    encode(fn, &m.qm, p.q, 2, dims, st, bqm, QBOX ? CU_TENSOR_MAP_SWIZZLE_NONE : CU_TENSOR_MAP_SWIZZLE_128B);
    encode(fn, &m.qt, p.q, 2, dims, st, bqt, CU_TENSOR_MAP_SWIZZLE_32B);
    encode(fn, &m.om, p.out, 2, dims, st, bom, QBOX ? CU_TENSOR_MAP_SWIZZLE_NONE : CU_TENSOR_MAP_SWIZZLE_128B);
    encode(fn, &m.ot, p.out, 2, dims, st, bot, CU_TENSOR_MAP_SWIZZLE_32B);
  }
  fused_kernel<<<NCTA, NTHR, SMEM_BYTES>>>(m, p);
}
```

```cpp
#include <cuda.h>
#include <cuda_bf16.h>
#include <cuda_runtime.h>
#include <stdint.h>

namespace {

constexpr int SEQ = 2048, DIM = 640, NCTA = 128, NTHR = 512;

#define TRIG_KB 9
#define KV_KB 2
#define DEV_EXIT 0
#define ATT_GATE 0
#define G_AFTER 0
#define FENCE_LO 0
#define FENCE_HI 0
#define PW1 2
#define PW2 1
#define ENDBAR 0
#define PAD_KB 0
#define Y_ALIAS 1
#define NOMB 0
#define SRC_ROT 0
#define WAIT_NS 0
#define WB_TRIG B_USIG
#define G_POS 0
#define TAILF 1
#define T_ISSUE 384
#define T_PF 416
#define T_INIT 448
#define ATT_MERGE 0
#define BMAP 1
#define PRE2 1
#define KV_MIX 0
#define O_DEFER 0
#define TASK0 0x3
#define TASK1 0x52
#define TASK2 0x41
#define HALO_FIRST 1
#define PREV_EARLY 0
#define Y_RB 2
#define O_RB 2
#define O_EAGER 1
#define OP_TRIG B_ATTN
#define FUSE_MIX 1
#define Q_EARLY 1
#define U_TRIM 1
#define Q_SLOT 3
#define G_TMA 1
#define W_RB 1
#define WPF B_S3
#define WPF_LIN 1
#define QBOX 0
#define O_SPLIT 2
#define ACQ 0
#define U_TMA 0
#define U_GATE 0
#define RF_GATE 0
#define WO_TRIG B_WST
#define WL_TRIG B_WOP
#define WO_GATE 4

constexpr uint32_t STAGE_BYTES = 47104, ST_W = 16384, ST_WT = 40960;
constexpr uint32_t O_BYTES = 20480, WO_BYTES = 12800;
constexpr uint32_t OFF_OA = 0;
constexpr uint32_t OFF_QS = Q_SLOT * O_BYTES, OFF_QT = OFF_QS + 16384;
constexpr uint32_t OFF_WC = 81920;
constexpr uint32_t OFF_WA = 94720;
constexpr uint32_t OFF_GATE = 145920;
constexpr uint32_t OFF_TT = 146432;
constexpr uint32_t OFF_KVX = 148480;
constexpr uint32_t OFF_CH3 = 163840;
constexpr uint32_t CH_BYTES = 12288, U_BYTES = 4096;
constexpr uint32_t OFF_FT = 225280, OFF_GT = 229376;
constexpr uint32_t OFF_CH0 = 188416;
constexpr uint32_t OFF_KVS = OFF_CH0, KVS_V = 4480, KVS_BYTES = 8576;
constexpr uint32_t OFF_WS = OFF_WA;
__device__ __forceinline__ uint32_t off_us(int s) { return OFF_CH0 + 4096 * ((0x65320 >> (4 * s)) & 7); }
constexpr uint32_t OFF_YT = 163840;
constexpr uint32_t OFF_BAR = 231936;
constexpr uint32_t SMEM_BYTES = OFF_BAR + 512;

enum : uint32_t {
  B_FULL1 = 0, B_EMPTY1 = 4, B_S3 = 7, B_FULL2 = 52, B_EMPTY2 = 13, B_U = 8, B_GATE = 12, B_HA = 19, B_HB = 20,
  B_ATTN = 21, B_C34 = 22, B_YRB = 23, B_YFULL = 24, B_EPOCH = 25, B_PREP = 26, B_P1 = 27, B_LAST = 28,
  B_E3 = 29, B_OSIG = 30, B_WOP = 31, B_USIG = 32, B_WST = 33, B_KV = 34, B_KVD = 39, B_QF = 17, B_ATT2 = 18, B_YST = 40,
  B_ORB = 45, B_CVD = 33 + 14, B_US = 45, B_YSIG = 50
};
constexpr uint32_t OFF_EPOCH = OFF_BAR + 8 * 51, OFF_D = OFF_BAR + 8 * 60;
__device__ __forceinline__ uint32_t off_o(int j) { return j < 4 ? OFF_OA + j * O_BYTES : j < 6 ? OFF_CH0 + (j - 4) * O_BYTES : OFF_OA + (j - 6) * O_BYTES; }
__device__ __forceinline__ uint32_t off_w(int j) { return j < 4 ? OFF_WA + j * WO_BYTES : j == 4 ? OFF_KVX : j == 5 ? OFF_WC : OFF_WA + (j - 6) * WO_BYTES; }
__device__ __forceinline__ int step_src(int hg, int j) {
  if (SRC_ROT == 2) {
    const int pos = (0x37621540 >> (4 * hg)) & 7;
    return j == 0 ? hg : (0x65217430 >> (4 * (j <= pos ? j - 1 : j))) & 7;
  }
  return SRC_ROT ? (hg + j) & 7 : j == 0 ? hg : j <= hg ? j - 1 : j;
}
__device__ __forceinline__ bool tail_first(int hg) { return TAILF && (hg & 3) == 3; }
__device__ __forceinline__ uint32_t off_ch(int c) { return (c < 3 ? OFF_CH0 : OFF_CH3 - 3 * CH_BYTES) + c * CH_BYTES; }

#define U_PITCH 264
__device__ __align__(1024) uint4 g_U[DIM * U_PITCH];
__device__ uint4 g_O[NCTA * 1280];
#define g_Y g_U
constexpr int Y_PITCH = U_PITCH;
__device__ uint4 g_WO[64 * 800];
__device__ uint4 g_halo[NCTA * 2 * 7 * 32];
__device__ __align__(128) float g_gate[SEQ + PAD_KB * 256];
__device__ unsigned g_cnt[32 * (1 + 2 * 16 + 8 + NCTA)];
constexpr int C_LAUNCH = 0, C_PREP = 32, C_Y = 32 * 17, C_W = 32 * 33, C_O = 32 * 41;

#define TSM(cond, slot) do { } while (0)
#define TSIF(cond, slot) do { if (__LINE__ >= FENCE_LO && __LINE__ < FENCE_HI) sched_fence(); } while (0)
__device__ __forceinline__ void sched_fence() {
  asm volatile("{\n.reg .pred p;\n.reg .u32 c;\nmov.u32 c, %%clock;\nsetp.eq.u32 p, c, 0;\n@p st.shared.u32 [%0], c;\n}"
               ::"r"(1024 + OFF_EPOCH + 4) : "memory");
}
#define TS(slot) TSIF(true, slot)

struct Params {
  const __nv_bfloat16 *q, *k, *v, *shift_k, *ssm_k, *ssm_D, *wqkv, *wo, *gate_w;
  __nv_bfloat16* out;
  uint32_t zero;
};

#define POLL_NS 0
constexpr int SPIN_LIMIT = 1 << 17;

__device__ __forceinline__ void mbar_init(uint32_t bar, uint32_t count) {
  asm volatile("mbarrier.init.shared::cta.b64 [%0], %1;" ::"r"(bar), "r"(count) : "memory");
}
__device__ __forceinline__ void mbar_expect_tx(uint32_t bar, uint32_t bytes) {
  asm volatile("mbarrier.arrive.expect_tx.shared::cta.b64 _, [%0], %1;" ::"r"(bar), "r"(bytes) : "memory");
}
__device__ __forceinline__ void mbar_arrive(uint32_t bar) {
  asm volatile("mbarrier.arrive.shared::cta.b64 _, [%0];" ::"r"(bar) : "memory");
}
__device__ __forceinline__ void mbar_wait(uint32_t bar, uint32_t parity) {
  uint32_t ok;
  int spins = 0;
  do {
    if (WAIT_NS)
      asm volatile("{\n.reg .pred p;\nmbarrier.try_wait.parity.shared::cta.b64 p, [%1], %2, %3;\nselp.b32 %0, 1, 0, p;\n}"
                   : "=r"(ok) : "r"(bar), "r"(parity), "r"(WAIT_NS) : "memory");
    else
      asm volatile("{\n.reg .pred p;\nmbarrier.try_wait.parity.shared::cta.b64 p, [%1], %2;\nselp.b32 %0, 1, 0, p;\n}"
                   : "=r"(ok) : "r"(bar), "r"(parity) : "memory");
    if (++spins > SPIN_LIMIT) break;
  } while (!ok);
}
__device__ __forceinline__ unsigned flag_read(const unsigned* p) {
  unsigned v;
  asm volatile("ld.relaxed.gpu.global.u32 %0, [%1];" : "=r"(v) : "l"(p) : "memory");
  return v;
}
__device__ __forceinline__ void flag_poll(const unsigned* p, unsigned target) {
  unsigned v;
  int spins = 0;
  do {
    if (POLL_NS && spins) __nanosleep(POLL_NS);
    asm volatile("ld.relaxed.gpu.global.u32 %0, [%1];" : "=r"(v) : "l"(p) : "memory");
    if (++spins > SPIN_LIMIT) break;
  } while ((int)(v - target) < 0);
}
__device__ __forceinline__ void flag_wait(const unsigned* p, unsigned target) {
  flag_poll(p, target);
  if (ACQ) asm volatile("fence.acquire.gpu;\nfence.proxy.async.global;" ::: "memory");
}
__device__ __forceinline__ void flag_signal(unsigned* p, int n, int lane) {
  if (lane == 0) asm volatile("fence.release.gpu;" ::: "memory");
  __syncwarp();
  if (lane < n) asm volatile("red.relaxed.gpu.global.add.u32 [%0], 1;" ::"l"(p + 32 * lane) : "memory");
}
__device__ __forceinline__ void flag_bump(unsigned* p) {
  asm volatile("red.relaxed.gpu.global.add.u32 [%0], 1;" ::"l"(p) : "memory");
}
__device__ __forceinline__ void fence_async_smem() { asm volatile("fence.proxy.async.shared::cta;" ::: "memory"); }
__device__ __forceinline__ void wg_sync(int id) { asm volatile("bar.sync %0, 128;" ::"r"(id) : "memory"); }

__device__ __forceinline__ void tma_2d(uint32_t dst, const CUtensorMap* tm, int c0, int c1, uint32_t bar) {
  asm volatile("cp.async.bulk.tensor.2d.shared::cluster.global.mbarrier::complete_tx::bytes [%0], [%1, {%3, %4}], [%2];"
               ::"r"(dst), "l"(tm), "r"(bar), "r"(c0), "r"(c1) : "memory");
}
__device__ __forceinline__ void tma_3d(uint32_t dst, const CUtensorMap* tm, int c0, int c1, int c2, uint32_t bar) {
  asm volatile("cp.async.bulk.tensor.3d.shared::cluster.global.mbarrier::complete_tx::bytes [%0], [%1, {%3, %4, %5}], [%2];"
               ::"r"(dst), "l"(tm), "r"(bar), "r"(c0), "r"(c1), "r"(c2) : "memory");
}
__device__ __forceinline__ void bulk_load(uint32_t dst, const void* src, uint32_t bytes, uint32_t bar) {
  asm volatile("cp.async.bulk.shared::cluster.global.mbarrier::complete_tx::bytes [%0], [%1], %2, [%3];"
               ::"r"(dst), "l"(src), "r"(bytes), "r"(bar) : "memory");
}
__device__ __forceinline__ void bulk_store(void* dst, uint32_t src, uint32_t bytes) {
  asm volatile("cp.async.bulk.global.shared::cta.bulk_group [%0], [%1], %2;\ncp.async.bulk.commit_group;"
               ::"l"(dst), "r"(src), "r"(bytes) : "memory");
}
template <int N> __device__ __forceinline__ void bulk_wait_read() { asm volatile("cp.async.bulk.wait_group.read %0;" ::"n"(N) : "memory"); }
__device__ __forceinline__ void tm_prefetch(const CUtensorMap* tm) {
  asm volatile("prefetch.tensormap [%0];" ::"l"(tm) : "memory");
}

__device__ __forceinline__ void wg_fence() { asm volatile("wgmma.fence.sync.aligned;" ::: "memory"); }
__device__ __forceinline__ void wg_commit() { asm volatile("wgmma.commit_group.sync.aligned;" ::: "memory"); }
template <int N> __device__ __forceinline__ void wg_wait() { asm volatile("wgmma.wait_group.sync.aligned %0;" ::"n"(N) : "memory"); }
__device__ __forceinline__ uint32_t desc_lo(uint32_t addr, uint32_t lbo) { return ((addr & 0x3FFFF) >> 4) | ((lbo >> 4) << 16); }
constexpr uint32_t desc_hi(uint32_t sbo, uint32_t swz) { return (sbo >> 4) | (swz << 30); }
constexpr uint32_t HI_SW128 = desc_hi(1024, 1), HI_SW64 = desc_hi(512, 2), HI_SW32 = desc_hi(256, 3), HI_NONE = desc_hi(128, 0);
template <int N> __device__ __forceinline__ void pin(float* d) {
#pragma unroll
  for (int i = 0; i < N; i++) asm volatile("" : "+f"(d[i])::"memory");
}

__device__ __forceinline__ uint32_t lds32(uint32_t a) {
  uint32_t v;
  asm volatile("ld.volatile.shared.u32 %0, [%1];" : "=r"(v) : "r"(a) : "memory");
  return v;
}
__device__ __forceinline__ uint4 ldg128(const void* a) {
  uint4 v;
  asm volatile("ld.global.nc.v4.u32 {%0, %1, %2, %3}, [%4];" : "=r"(v.x), "=r"(v.y), "=r"(v.z), "=r"(v.w) : "l"(a) : "memory");
  return v;
}
__device__ __forceinline__ uint2 ldg64(const void* a) {
  uint2 v;
  asm volatile("ld.global.nc.v2.u32 {%0, %1}, [%2];" : "=r"(v.x), "=r"(v.y) : "l"(a) : "memory");
  return v;
}
__device__ __forceinline__ void ldsm4(uint32_t* r, uint32_t a) {
  asm volatile("ldmatrix.sync.aligned.m8n8.x4.shared.b16 {%0, %1, %2, %3}, [%4];"
               : "=r"(r[0]), "=r"(r[1]), "=r"(r[2]), "=r"(r[3]) : "r"(a) : "memory");
}
__device__ __forceinline__ void ldsm4t(uint32_t* r, uint32_t a) {
  asm volatile("ldmatrix.sync.aligned.m8n8.x4.trans.shared.b16 {%0, %1, %2, %3}, [%4];"
               : "=r"(r[0]), "=r"(r[1]), "=r"(r[2]), "=r"(r[3]) : "r"(a) : "memory");
}
__device__ __forceinline__ uint2 lds64(uint32_t a) {
  uint2 v;
  asm volatile("ld.shared.v2.u32 {%0, %1}, [%2];" : "=r"(v.x), "=r"(v.y) : "r"(a) : "memory");
  return v;
}
__device__ __forceinline__ uint4 lds128(uint32_t a) {
  uint4 v;
  asm volatile("ld.shared.v4.u32 {%0, %1, %2, %3}, [%4];" : "=r"(v.x), "=r"(v.y), "=r"(v.z), "=r"(v.w) : "r"(a) : "memory");
  return v;
}
__device__ __forceinline__ void sts128(uint32_t a, uint32_t x, uint32_t y, uint32_t z, uint32_t w) {
  asm volatile("st.shared.v4.u32 [%0], {%1, %2, %3, %4};" ::"r"(a), "r"(x), "r"(y), "r"(z), "r"(w) : "memory");
}
__device__ __forceinline__ void stsm4(uint32_t a, const uint32_t* r) {
  asm volatile("stmatrix.sync.aligned.m8n8.x4.shared.b16 [%0], {%1, %2, %3, %4};" ::"r"(a), "r"(r[0]), "r"(r[1]), "r"(r[2]), "r"(r[3]) : "memory");
}
__device__ __forceinline__ void stsm4t(uint32_t a, const uint32_t* r) {
  asm volatile("stmatrix.sync.aligned.m8n8.x4.trans.shared.b16 [%0], {%1, %2, %3, %4};" ::"r"(a), "r"(r[0]), "r"(r[1]), "r"(r[2]), "r"(r[3]) : "memory");
}
__device__ __forceinline__ uint32_t pack2(float lo, float hi) {
  uint32_t r;
  asm("cvt.rn.bf16x2.f32 %0, %1, %2;" : "=r"(r) : "f"(hi), "f"(lo));
  return r;
}
__device__ __forceinline__ uint32_t movm(uint32_t a) {
  uint32_t d;
  asm volatile("movmatrix.sync.aligned.m8n8.trans.b16 %0, %1;" : "=r"(d) : "r"(a));
  return d;
}
__device__ __forceinline__ uint32_t bmul(uint32_t a, uint32_t b) {
  uint32_t d;
  asm("mul.rn.bf16x2 %0, %1, %2;" : "=r"(d) : "r"(a), "r"(b));
  return d;
}
__device__ __forceinline__ uint32_t badd(uint32_t a, uint32_t b) {
  uint32_t d;
  asm("add.rn.bf16x2 %0, %1, %2;" : "=r"(d) : "r"(a), "r"(b));
  return d;
}
__device__ __forceinline__ uint32_t bfma(uint32_t a, uint32_t b, uint32_t c) {
  uint32_t d;
  asm("fma.rn.bf16x2 %0, %1, %2, %3;" : "=r"(d) : "r"(a), "r"(b), "r"(c));
  return d;
}
__device__ __forceinline__ float bf_lo(uint32_t x) { return __uint_as_float(x << 16); }
__device__ __forceinline__ float bf_hi(uint32_t x) { return __uint_as_float(x & 0xFFFF0000u); }
__device__ __forceinline__ float ex2(float x) {
  float y;
  asm("ex2.approx.ftz.f32 %0, %1;" : "=f"(y) : "f"(x));
  return y;
}
__device__ __forceinline__ float rcp(float x) {
  float y;
  asm("rcp.approx.ftz.f32 %0, %1;" : "=f"(y) : "f"(x));
  return y;
}
__device__ __forceinline__ void mma16816(float* d, uint32_t a0, uint32_t a1, uint32_t a2, uint32_t a3, uint32_t b0, uint32_t b1) {
  asm volatile("mma.sync.aligned.m16n8k16.row.col.f32.bf16.bf16.f32 {%0, %1, %2, %3}, {%4, %5, %6, %7}, {%8, %9}, {%0, %1, %2, %3};"
               : "+f"(d[0]), "+f"(d[1]), "+f"(d[2]), "+f"(d[3])
               : "r"(a0), "r"(a1), "r"(a2), "r"(a3), "r"(b0), "r"(b1));
}
__device__ __forceinline__ void mma1688(float* d, uint32_t a0, uint32_t a1, uint32_t b0) {
  asm volatile("mma.sync.aligned.m16n8k8.row.col.f32.bf16.bf16.f32 {%0, %1, %2, %3}, {%4, %5}, {%6}, {%0, %1, %2, %3};"
               : "+f"(d[0]), "+f"(d[1]), "+f"(d[2]), "+f"(d[3])
               : "r"(a0), "r"(a1), "r"(b0));
}

template <int N> struct WgRS;
template <int N> struct WgSST;
template <> struct WgRS<32> {
  template <uint32_t HB>
  static __device__ __forceinline__ void mma(float* d, const uint32_t* a, uint32_t db) {
    asm volatile("{\n.reg .pred p;\n.reg .b64 db;\nsetp.ne.b32 p, %22, 0;\n"
      "mov.b64 db, {%20, %21};\n"
      "wgmma.mma_async.sync.aligned.m64n32k16.f32.bf16.bf16 {"
      "%0, %1, %2, %3, %4, %5, %6, %7, %8, %9, %10, %11, %12, %13, %14, %15"
      "}, {%16, %17, %18, %19}, db, p, 1, 1, 1;\n}\n"
      : "+f"(d[0]), "+f"(d[1]), "+f"(d[2]), "+f"(d[3]), "+f"(d[4]), "+f"(d[5]), "+f"(d[6]), "+f"(d[7]),
        "+f"(d[8]), "+f"(d[9]), "+f"(d[10]), "+f"(d[11]), "+f"(d[12]), "+f"(d[13]), "+f"(d[14]), "+f"(d[15])
      : "r"(a[0]), "r"(a[1]), "r"(a[2]), "r"(a[3]), "r"(db), "n"(HB), "n"(1));
  }
  template <uint32_t HB>
  static __device__ __forceinline__ void set(float* d, const uint32_t* a, uint32_t db) {
    asm volatile("{\n.reg .pred p;\n.reg .b64 db;\nsetp.ne.b32 p, %22, 0;\n"
      "mov.b64 db, {%20, %21};\n"
      "wgmma.mma_async.sync.aligned.m64n32k16.f32.bf16.bf16 {"
      "%0, %1, %2, %3, %4, %5, %6, %7, %8, %9, %10, %11, %12, %13, %14, %15"
      "}, {%16, %17, %18, %19}, db, p, 1, 1, 1;\n}\n"
      : "=f"(d[0]), "=f"(d[1]), "=f"(d[2]), "=f"(d[3]), "=f"(d[4]), "=f"(d[5]), "=f"(d[6]), "=f"(d[7]),
        "=f"(d[8]), "=f"(d[9]), "=f"(d[10]), "=f"(d[11]), "=f"(d[12]), "=f"(d[13]), "=f"(d[14]), "=f"(d[15])
      : "r"(a[0]), "r"(a[1]), "r"(a[2]), "r"(a[3]), "r"(db), "n"(HB), "n"(0));
  }
};
template <> struct WgRS<64> {
  template <uint32_t HB>
  static __device__ __forceinline__ void mma(float* d, const uint32_t* a, uint32_t db) {
    asm volatile("{\n.reg .pred p;\n.reg .b64 db;\nsetp.ne.b32 p, %38, 0;\n"
      "mov.b64 db, {%36, %37};\n"
      "wgmma.mma_async.sync.aligned.m64n64k16.f32.bf16.bf16 {"
      "%0, %1, %2, %3, %4, %5, %6, %7, %8, %9, %10, %11, %12, %13, %14, %15, "
      "%16, %17, %18, %19, %20, %21, %22, %23, %24, %25, %26, %27, %28, %29, %30, %31"
      "}, {%32, %33, %34, %35}, db, p, 1, 1, 1;\n}\n"
      : "+f"(d[0]), "+f"(d[1]), "+f"(d[2]), "+f"(d[3]), "+f"(d[4]), "+f"(d[5]), "+f"(d[6]), "+f"(d[7]),
        "+f"(d[8]), "+f"(d[9]), "+f"(d[10]), "+f"(d[11]), "+f"(d[12]), "+f"(d[13]), "+f"(d[14]), "+f"(d[15]),
        "+f"(d[16]), "+f"(d[17]), "+f"(d[18]), "+f"(d[19]), "+f"(d[20]), "+f"(d[21]), "+f"(d[22]), "+f"(d[23]),
        "+f"(d[24]), "+f"(d[25]), "+f"(d[26]), "+f"(d[27]), "+f"(d[28]), "+f"(d[29]), "+f"(d[30]), "+f"(d[31])
      : "r"(a[0]), "r"(a[1]), "r"(a[2]), "r"(a[3]), "r"(db), "n"(HB), "n"(1));
  }
  template <uint32_t HB>
  static __device__ __forceinline__ void set(float* d, const uint32_t* a, uint32_t db) {
    asm volatile("{\n.reg .pred p;\n.reg .b64 db;\nsetp.ne.b32 p, %38, 0;\n"
      "mov.b64 db, {%36, %37};\n"
      "wgmma.mma_async.sync.aligned.m64n64k16.f32.bf16.bf16 {"
      "%0, %1, %2, %3, %4, %5, %6, %7, %8, %9, %10, %11, %12, %13, %14, %15, "
      "%16, %17, %18, %19, %20, %21, %22, %23, %24, %25, %26, %27, %28, %29, %30, %31"
      "}, {%32, %33, %34, %35}, db, p, 1, 1, 1;\n}\n"
      : "=f"(d[0]), "=f"(d[1]), "=f"(d[2]), "=f"(d[3]), "=f"(d[4]), "=f"(d[5]), "=f"(d[6]), "=f"(d[7]),
        "=f"(d[8]), "=f"(d[9]), "=f"(d[10]), "=f"(d[11]), "=f"(d[12]), "=f"(d[13]), "=f"(d[14]), "=f"(d[15]),
        "=f"(d[16]), "=f"(d[17]), "=f"(d[18]), "=f"(d[19]), "=f"(d[20]), "=f"(d[21]), "=f"(d[22]), "=f"(d[23]),
        "=f"(d[24]), "=f"(d[25]), "=f"(d[26]), "=f"(d[27]), "=f"(d[28]), "=f"(d[29]), "=f"(d[30]), "=f"(d[31])
      : "r"(a[0]), "r"(a[1]), "r"(a[2]), "r"(a[3]), "r"(db), "n"(HB), "n"(0));
  }
};
template <> struct WgSST<48> {
  template <uint32_t HA, uint32_t HB>
  static __device__ __forceinline__ void mma(float* d, uint32_t da, uint32_t db, int sc) {
    asm volatile("{\n.reg .pred p;\n.reg .b64 da, db;\nsetp.ne.b32 p, %28, 0;\n"
      "mov.b64 da, {%24, %25};\nmov.b64 db, {%26, %27};\n"
      "wgmma.mma_async.sync.aligned.m64n48k16.f32.bf16.bf16 {"
      "%0, %1, %2, %3, %4, %5, %6, %7, %8, %9, %10, %11, %12, %13, %14, %15, "
      "%16, %17, %18, %19, %20, %21, %22, %23"
      "}, da, db, p, 1, 1, 0, 1;\n}\n"
      : "+f"(d[0]), "+f"(d[1]), "+f"(d[2]), "+f"(d[3]), "+f"(d[4]), "+f"(d[5]), "+f"(d[6]), "+f"(d[7]),
        "+f"(d[8]), "+f"(d[9]), "+f"(d[10]), "+f"(d[11]), "+f"(d[12]), "+f"(d[13]), "+f"(d[14]), "+f"(d[15]),
        "+f"(d[16]), "+f"(d[17]), "+f"(d[18]), "+f"(d[19]), "+f"(d[20]), "+f"(d[21]), "+f"(d[22]), "+f"(d[23])
      : "r"(da), "n"(HA), "r"(db), "n"(HB), "r"(sc));
  }
};
template <> struct WgSST<80> {
  template <uint32_t HA, uint32_t HB>
  static __device__ __forceinline__ void mma(float* d, uint32_t da, uint32_t db, int sc) {
    asm volatile("{\n.reg .pred p;\n.reg .b64 da, db;\nsetp.ne.b32 p, %44, 0;\n"
      "mov.b64 da, {%40, %41};\nmov.b64 db, {%42, %43};\n"
      "wgmma.mma_async.sync.aligned.m64n80k16.f32.bf16.bf16 {"
      "%0, %1, %2, %3, %4, %5, %6, %7, %8, %9, %10, %11, %12, %13, %14, %15, "
      "%16, %17, %18, %19, %20, %21, %22, %23, %24, %25, %26, %27, %28, %29, %30, %31, "
      "%32, %33, %34, %35, %36, %37, %38, %39"
      "}, da, db, p, 1, 1, 0, 1;\n}\n"
      : "+f"(d[0]), "+f"(d[1]), "+f"(d[2]), "+f"(d[3]), "+f"(d[4]), "+f"(d[5]), "+f"(d[6]), "+f"(d[7]),
        "+f"(d[8]), "+f"(d[9]), "+f"(d[10]), "+f"(d[11]), "+f"(d[12]), "+f"(d[13]), "+f"(d[14]), "+f"(d[15]),
        "+f"(d[16]), "+f"(d[17]), "+f"(d[18]), "+f"(d[19]), "+f"(d[20]), "+f"(d[21]), "+f"(d[22]), "+f"(d[23]),
        "+f"(d[24]), "+f"(d[25]), "+f"(d[26]), "+f"(d[27]), "+f"(d[28]), "+f"(d[29]), "+f"(d[30]), "+f"(d[31]),
        "+f"(d[32]), "+f"(d[33]), "+f"(d[34]), "+f"(d[35]), "+f"(d[36]), "+f"(d[37]), "+f"(d[38]), "+f"(d[39])
      : "r"(da), "n"(HA), "r"(db), "n"(HB), "r"(sc));
  }
};
template <> struct WgSST<192> {
  template <uint32_t HA, uint32_t HB>
  static __device__ __forceinline__ void mma(float* d, uint32_t da, uint32_t db, int sc) {
    asm volatile("{\n.reg .pred p;\n.reg .b64 da, db;\nsetp.ne.b32 p, %100, 0;\n"
      "mov.b64 da, {%96, %97};\nmov.b64 db, {%98, %99};\n"
      "wgmma.mma_async.sync.aligned.m64n192k16.f32.bf16.bf16 {"
      "%0, %1, %2, %3, %4, %5, %6, %7, %8, %9, %10, %11, %12, %13, %14, %15, "
      "%16, %17, %18, %19, %20, %21, %22, %23, %24, %25, %26, %27, %28, %29, %30, %31, "
      "%32, %33, %34, %35, %36, %37, %38, %39, %40, %41, %42, %43, %44, %45, %46, %47, "
      "%48, %49, %50, %51, %52, %53, %54, %55, %56, %57, %58, %59, %60, %61, %62, %63, "
      "%64, %65, %66, %67, %68, %69, %70, %71, %72, %73, %74, %75, %76, %77, %78, %79, "
      "%80, %81, %82, %83, %84, %85, %86, %87, %88, %89, %90, %91, %92, %93, %94, %95"
      "}, da, db, p, 1, 1, 0, 1;\n}\n"
      : "+f"(d[0]), "+f"(d[1]), "+f"(d[2]), "+f"(d[3]), "+f"(d[4]), "+f"(d[5]), "+f"(d[6]), "+f"(d[7]),
        "+f"(d[8]), "+f"(d[9]), "+f"(d[10]), "+f"(d[11]), "+f"(d[12]), "+f"(d[13]), "+f"(d[14]), "+f"(d[15]),
        "+f"(d[16]), "+f"(d[17]), "+f"(d[18]), "+f"(d[19]), "+f"(d[20]), "+f"(d[21]), "+f"(d[22]), "+f"(d[23]),
        "+f"(d[24]), "+f"(d[25]), "+f"(d[26]), "+f"(d[27]), "+f"(d[28]), "+f"(d[29]), "+f"(d[30]), "+f"(d[31]),
        "+f"(d[32]), "+f"(d[33]), "+f"(d[34]), "+f"(d[35]), "+f"(d[36]), "+f"(d[37]), "+f"(d[38]), "+f"(d[39]),
        "+f"(d[40]), "+f"(d[41]), "+f"(d[42]), "+f"(d[43]), "+f"(d[44]), "+f"(d[45]), "+f"(d[46]), "+f"(d[47]),
        "+f"(d[48]), "+f"(d[49]), "+f"(d[50]), "+f"(d[51]), "+f"(d[52]), "+f"(d[53]), "+f"(d[54]), "+f"(d[55]),
        "+f"(d[56]), "+f"(d[57]), "+f"(d[58]), "+f"(d[59]), "+f"(d[60]), "+f"(d[61]), "+f"(d[62]), "+f"(d[63]),
        "+f"(d[64]), "+f"(d[65]), "+f"(d[66]), "+f"(d[67]), "+f"(d[68]), "+f"(d[69]), "+f"(d[70]), "+f"(d[71]),
        "+f"(d[72]), "+f"(d[73]), "+f"(d[74]), "+f"(d[75]), "+f"(d[76]), "+f"(d[77]), "+f"(d[78]), "+f"(d[79]),
        "+f"(d[80]), "+f"(d[81]), "+f"(d[82]), "+f"(d[83]), "+f"(d[84]), "+f"(d[85]), "+f"(d[86]), "+f"(d[87]),
        "+f"(d[88]), "+f"(d[89]), "+f"(d[90]), "+f"(d[91]), "+f"(d[92]), "+f"(d[93]), "+f"(d[94]), "+f"(d[95])
      : "r"(da), "n"(HA), "r"(db), "n"(HB), "r"(sc));
  }
};

struct FftConst {
  uint32_t f[2][4], fi[4][4];
  uint32_t ta[2][2], tb[2][2];
};
__device__ __forceinline__ void cis(int m, float scale, float& c, float& s) {
  const float a = (float)m * (-6.283185307179586f * scale);
  c = __cosf(a);
  s = __sinf(a);
}
__device__ __forceinline__ void fft_tables(uint32_t (&v)[12], int tw) {
  const int row = tw >> 2, ch = tw & 3;
#pragma unroll
  for (int i = 0; i < 4; i++) {
    float c[2], s[2], x[2];
#pragma unroll
    for (int e = 0; e < 2; e++) {
      cis((((32 * (8 * ch + 2 * i + e) + 15) * (4 * row - 63) + 2048) & 4095) - 2048, 1.f / 4096, c[e], s[e]);
      float gc, gs;
      cis((((row & 15) * (8 * (ch & 1) + 2 * i + e) + 8) & 15) - 8, 1.f / 16, gc, gs);
      x[e] = (row >> 4) == (ch >> 1) ? gc : (ch >> 1) ? gs : -gs;
    }
    v[i] = pack2(c[0] * 0.125f, c[1] * 0.125f);
    v[4 + i] = pack2(s[0] * 0.125f, s[1] * 0.125f);
    v[8 + i] = pack2(x[0], x[1]);
  }
#pragma unroll
  for (int i = 0; i < 12; i++) asm volatile("" : "+r"(v[i]));
}
__device__ __forceinline__ void fft_tables_store(const uint32_t (&v)[12], uint32_t sb, int tw) {
  const int row = tw >> 2;
  const uint32_t x = ((tw ^ (row >> 1)) & 3) << 4, a = sb + OFF_FT + (16 * (row >> 3) + (row & 7)) * 64 + x;
  sts128(a, v[0], v[1], v[2], v[3]);
  sts128(a + 512, v[4], v[5], v[6], v[7]);
  sts128(sb + OFF_GT + row * 64 + x, v[8], v[9], v[10], v[11]);
}
__device__ __forceinline__ void fft_twiddles(uint32_t (&v)[2], int tw) {
  float a[2], s[2];
#pragma unroll
  for (int i = 0; i < 2; i++) {
    float c;
    cis((2 * (2 * (tw & 3) + i) - 15) * (4 * (tw >> 2) - 63), 1.f / 4096, c, s[i]);
    a[i] = __fdividef(-s[i], 1.f + c);
  }
  v[0] = pack2(a[0], a[1]);
  v[1] = pack2(s[0], s[1]);
  asm volatile("" : "+r"(v[0]), "+r"(v[1]));
}
__device__ __forceinline__ void fft_matrices(FftConst& k, uint32_t sb, int w, int lane) {
  const uint32_t x = (lane >> 1) & 3;
  const uint2 t0 = lds64(sb + OFF_TT + 256 * w + 8 * lane), t1 = lds64(sb + OFF_TT + 256 * w + 8 * (lane ^ 3));
  k.ta[0][0] = t0.x;
  k.tb[0][0] = t0.y;
  k.ta[1][1] = __byte_perm(t1.x, 0, 0x1032);
  k.tb[1][1] = __byte_perm(t1.y, 0, 0x1032);
#pragma unroll
  for (int j = 0; j < 2; j++) {
    k.ta[1 - j][j] = k.ta[j][j] ^ 0x80008000u;
    k.tb[1 - j][j] = k.tb[j][j] ^ 0x80008000u;
    asm volatile("" : "+r"(k.ta[0][j]), "+r"(k.tb[0][j]), "+r"(k.ta[1][j]), "+r"(k.tb[1][j]));
  }
#pragma unroll
  for (int i = 0; i < 2; i++) {
    ldsm4(k.f[i], sb + OFF_FT + (16 * w + (lane & 15)) * 64 + (((2 * i + (lane >> 4)) ^ x) << 4));
    ldsm4t(k.fi[i], sb + OFF_FT + (32 * i + lane) * 64 + ((w ^ x) << 4));
#pragma unroll
    for (int j = 0; j < 4; j++) {
      k.fi[2 + i][j] = (j & 1) ? k.fi[i][j - 1] ^ 0x80008000u : k.fi[i][j + 1];
      asm volatile("" : "+r"(k.fi[2 + i][j]));
    }
  }
}
__device__ __forceinline__ void rot(uint32_t& x, uint32_t& y, uint32_t a, uint32_t b) {
  x = bfma(a, y, x);
  y = bfma(b, x, y);
  x = bfma(a, y, x);
}
__device__ __forceinline__ void twiddle_fwd(uint32_t (&a)[4][4], float* d, const FftConst& k) {
#pragma unroll
  for (int q = 0; q < 4; q++)
#pragma unroll
    for (int j = 0; j < 2; j++) {
      const float* x = d + 8 * q + 4 * j;
      uint32_t re = pack2(x[0], x[1]), im = pack2(x[2], x[3]);
      rot(re, im, k.ta[0][j], k.tb[0][j]);
      a[q & 2][2 * j + (q & 1)] = re;
      a[(q & 2) + 1][2 * j + (q & 1)] = im;
    }
}
__device__ __forceinline__ void g_step(float* d, const uint32_t (&a)[4][4], uint32_t dre, uint32_t dim) {
  WgRS<32>::set<HI_SW64>(d, a[0], dre);
  WgRS<32>::set<HI_SW64>(d + 16, a[2], dre);
  WgRS<32>::mma<HI_SW64>(d, a[1], dim);
  WgRS<32>::mma<HI_SW64>(d + 16, a[3], dim);
  wg_commit();
}

__device__ __forceinline__ void products(uint32_t (&a)[4][4], const float* H, const float* U, int p) {
#pragma unroll
  for (int j = 0; j < 2; j++)
#pragma unroll
    for (int m = 2 * p; m < 2 * p + 2; m++) {
      float pr[2], pi[2];
#pragma unroll
      for (int x = 0; x < 2; x++)
#pragma unroll
        for (int q = 0; q <= m; q++) {
          const int ih = 16 * (q >> 1) + 2 * (q & 1) + 4 * j + x, iu = 16 * ((m - q) >> 1) + 2 * ((m - q) & 1) + 4 * j + x;
          pr[x] = q ? fmaf(H[ih], U[iu], pr[x]) : H[ih] * U[iu];
          pi[x] = q ? fmaf(H[ih], U[iu + 8], pi[x]) : H[ih] * U[iu + 8];
          pr[x] = fmaf(-H[ih + 8], U[iu + 8], pr[x]);
          pi[x] = fmaf(H[ih + 8], U[iu], pi[x]);
        }
      a[m & 2][2 * j + (m & 1)] = pack2(pr[0], pr[1]);
      a[(m & 2) + 1][2 * j + (m & 1)] = pack2(pi[0], pi[1]);
    }
}

__device__ __forceinline__ void f_step(float* d, const FftConst& k, uint32_t db) {
  WgRS<64>::set<HI_SW32>(d, k.f[0], db);
  WgRS<64>::mma<HI_SW32>(d, k.f[1], db + 32);
  wg_commit();
}
__device__ __forceinline__ void last_step(float* d, const FftConst& k, uint32_t dz) {
  wg_fence();
  WgRS<64>::set<HI_SW128>(d, k.fi[0], dz);
#pragma unroll
  for (int ks = 1; ks < 4; ks++) WgRS<64>::mma<HI_SW128>(d, k.fi[ks], dz + 128 * ks);
  wg_commit();
}
__device__ __forceinline__ void conv_channel(const FftConst& k, uint32_t (&a)[4][4], uint32_t sb, int c, int cn, int wg, int w, int lane) {
  const uint32_t cb = sb + off_ch(c), bars = sb + OFF_BAR;
  const uint32_t du = desc_lo(cb, 1024), dg = desc_lo(sb + OFF_GT, 16), dz = desc_lo(cb + U_BYTES, 16);
  float U[32], H[32];
  uint32_t e[4][4];
  const float dv = __uint_as_float(lds32(sb + OFF_D + 4 * c));
  if (ATT_GATE) mbar_wait(bars + 8 * (ATT_GATE == 1 ? B_ATTN : B_ATT2), 0);
  mbar_wait(bars + 8 * (B_U + (c < 3 ? c : 3)), 0);
  TSM(w == 0 && c < 3, 7 + wg);
  wg_fence();
  f_step(U, k, du);
  g_step(H, a, dg, dg + 64);
  wg_wait<1>();
  pin<32>(U);
  twiddle_fwd(e, U, k);
  wg_fence();
  g_step(U, e, dg, dg + 64);
  wg_wait<0>();
  pin<32>(U);
  pin<32>(H);
#pragma unroll
  for (int j = 0; j < 4; j++) H[4 * (j >> 1) + (j & 1)] += dv;
  float V[32];
#pragma unroll
  for (int p = 0; p < 2; p++) {
    products(a, H, U, p);
    wg_fence();
    WgRS<32>::set<HI_SW64>(V + 16 * p, a[2 * p], dg + 64);
    WgRS<32>::mma<HI_SW64>(V + 16 * p, a[2 * p + 1], dg);
    wg_commit();
  }
  const uint32_t za = cb + U_BYTES + (8 * w + (lane & 7)) * 128 + (((lane >> 3) ^ (lane & 7)) << 4);
  const uint32_t ya = cb + (lane >> 4) * 1024 + (8 * w + (lane & 7)) * 32 + ((((lane >> 3) ^ (lane >> 2)) & 1) << 4);
  wg_sync(1 + wg);
#pragma unroll
  for (int p = 0; p < 2; p++) {
    if (p == 0) wg_wait<1>();
    else wg_wait<0>();
    pin<16>(V + 16 * p);
#pragma unroll
    for (int i = 0; i < 4; i++) {
      const int j = i & 1;
      const float* x = V + 16 * p + 4 * j + (i & 2);
      e[p][i] = pack2(x[8], x[9]);
      e[2 + p][i] = pack2(x[0], x[1]);
      rot(e[p][i], e[2 + p][i], k.ta[1][j], k.tb[1][j]);
    }
    stsm4(za ^ (64 * p), e[p]);
    stsm4((za ^ (64 * p)) + 4096, e[2 + p]);
  }
  if (cn >= 0) {
    wg_fence();
    f_step(U, k, desc_lo(sb + off_ch(cn) + U_BYTES, 1024));
    fence_async_smem();
    wg_sync(1 + wg);
    last_step(H, k, dz);
    wg_wait<1>();
    pin<32>(U);
    twiddle_fwd(a, U, k);
    wg_wait<0>();
  } else {
    fence_async_smem();
    wg_sync(1 + wg);
    last_step(H, k, dz);
    wg_wait<0>();
  }
  pin<32>(H);
  if (WO_GATE == 4 && lane == 0) mbar_arrive(bars + 8 * B_CVD);
  TSIF(w == 0, 88 + c);
#pragma unroll
  for (int j = 0; j < 8; j++)
    e[j >> 2][j & 3] = j < 2 ? pack2(H[4 * j], H[4 * j + 1]) : pack2(H[4 * j] + H[4 * j - 6], H[4 * j + 1] + H[4 * j - 5]);
  stsm4(ya, e[0]);
  stsm4(ya + 2048, e[1]);
  fence_async_smem();
  __syncwarp();
}

__device__ __forceinline__ void prep_slab(uint4* res, const uint2* sw, uint32_t sb, int slab, int w, int lane) {
  const int t = lane & 3, tp = (lane & 7) >> 1, pos = 8 * tp + 2 * (((lane >> 3) + tp) & 3) + (lane & 1);
  const uint32_t base = sb + OFF_KVS + slab * KVS_BYTES + pos * 128;
  uint32_t kk[2][4][4], vv[2][4];
  mbar_wait(sb + OFF_BAR + 8 * (B_KV + slab), 0);
#pragma unroll
  for (int h = 0; h < 2; h++) {
#pragma unroll
    for (int j = 0; j < 4; j++) {
      const uint32_t a = base + 128 * j;
      ldsm4t(kk[h][j], a + (((w + 4 * h) ^ ((a >> 7) & 7)) << 4));
    }
    const uint32_t a = base + KVS_V;
    ldsm4t(vv[h], a + (((w + 4 * h) ^ ((a >> 7) & 7)) << 4));
  }
#pragma unroll
  for (int h = 0; h < 2; h++) {
    uint32_t (&k)[4][4] = kk[h];
    uint32_t (&v)[4] = vv[h];
    const uint32_t w0 = __byte_perm(sw[h].x, 0, 0x1010), w1 = __byte_perm(sw[h].x, 0, 0x3232);
    const uint32_t w2 = __byte_perm(sw[h].y, 0, 0x1010), w3 = __byte_perm(sw[h].y, 0, 0x3232);
#pragma unroll
    for (int m = 0; m < 4; m++)
      v[m] = bmul(badd(badd(badd(bmul(k[0][m], w3), bmul(k[1][m], w2)), bmul(k[2][m], w1)), bmul(k[3][m], w0)), v[m]);
    uint32_t a[4];
#pragma unroll
    for (int m = 0; m < 4; m++) a[m] = (t & 1) ? v[(m + 3) & 3] : v[m];
    res[h] = (t & 2) ? make_uint4(a[2], a[3], a[0], a[1]) : make_uint4(a[0], a[1], a[2], a[3]);
  }
}

__device__ __forceinline__ void prep_gate(const Params& p, uint32_t sb, int b, int w, int lane) {
  uint2 gw[5], x[4][5];
#pragma unroll
  for (int j = 0; j < 5; j++) gw[j] = ldg64(reinterpret_cast<const uint2*>(p.gate_w) + lane + 32 * j);
#pragma unroll
  for (int i = 0; i < 4; i++)
#pragma unroll
    for (int j = 0; j < 5; j++)
      x[i][j] = ldg64(reinterpret_cast<const uint2*>(p.q) + (16 * b + 4 * w + i) * (DIM / 4) + lane + 32 * j);
  float s[4];
#pragma unroll
  for (int i = 0; i < 4; i++) {
    s[i] = 0.f;
#pragma unroll
    for (int j = 0; j < 5; j++) {
      const uint32_t m0 = bmul(x[i][j].x, gw[j].x), m1 = bmul(x[i][j].y, gw[j].y);
      s[i] += (bf_lo(m0) + bf_hi(m0)) + (bf_lo(m1) + bf_hi(m1));
    }
  }
  const bool h = lane & 16, q = lane & 8;
  const float a = (h ? s[2] : s[0]) + __shfl_xor_sync(0xffffffffu, h ? s[0] : s[2], 16);
  const float c = (h ? s[3] : s[1]) + __shfl_xor_sync(0xffffffffu, h ? s[1] : s[3], 16);
  float z = (q ? c : a) + __shfl_xor_sync(0xffffffffu, q ? a : c, 8);
#pragma unroll
  for (int o = 4; o > 0; o >>= 1) z += __shfl_xor_sync(0xffffffffu, z, o);
  z = bf_lo(pack2(z, 0.f));
  z = bf_lo(pack2(__fdividef(1.f, 1.f + __expf(-z)), 0.f));
  if (G_TMA) {
    mbar_wait(sb + OFF_BAR + 8 * B_S3, 0);
    if ((lane & 7) == 0) asm volatile("st.shared.f32 [%0], %1;" ::"r"(sb + OFF_GATE + 64 * (b & 7) + 16 * w + (lane >> 1)), "f"(z) : "memory");
    fence_async_smem();
  } else if ((lane & 7) == 0) {
    g_gate[16 * b + 4 * w + (lane >> 3)] = z;
  }
}

__device__ __forceinline__ uint32_t bmax(uint32_t a, uint32_t b) {
  uint32_t d;
  asm("max.bf16x2 %0, %1, %2;" : "=r"(d) : "r"(a), "r"(b));
  return d;
}
__device__ __forceinline__ void softmax_two(const float (&l)[2][2], uint32_t& p0, uint32_t& p1) {
  constexpr float kScale = 0.22360679774997896f, kLog2e = 1.4426950408889634f;
  const uint32_t r0 = pack2(l[0][0], l[1][0]), r1 = pack2(l[0][1], l[1][1]);
  const uint32_t x0 = pack2(bf_lo(r0) * kScale, bf_hi(r0) * kScale), x1 = pack2(bf_lo(r1) * kScale, bf_hi(r1) * kScale);
  uint32_t m = bmax(x0, x1);
  m = bmax(m, __shfl_xor_sync(0xffffffffu, m, 1));
  m = bmax(m, __shfl_xor_sync(0xffffffffu, m, 2));
  const float m0 = bf_lo(m) * kLog2e, m1 = bf_hi(m) * kLog2e;
  p0 = pack2(ex2(bf_lo(x0) * kLog2e - m0), ex2(bf_lo(x1) * kLog2e - m0));
  p1 = pack2(ex2(bf_hi(x0) * kLog2e - m1), ex2(bf_hi(x1) * kLog2e - m1));
}

__device__ __forceinline__ void halo_read(uint32_t (&kpv)[10], uint32_t (&vpv)[10], uint32_t (&tg)[7], const uint4* hp) {
#pragma unroll
  for (int j = 0; j < 7; j++) {
    uint32_t x0, x1, x2;
    asm volatile("ld.relaxed.gpu.global.v4.u32 {%0, %1, %2, %3}, [%4];"
                 : "=r"(x0), "=r"(x1), "=r"(x2), "=r"(tg[j]) : "l"(hp + 32 * j) : "memory");
    if (j < 4) kpv[3 * j] = x0; else vpv[3 * j - 10] = x0;
    if (j < 3) kpv[3 * j + 1] = x1; else vpv[3 * j - 9] = x1;
    if (j < 3) kpv[3 * j + 2] = x2; else if (j < 6) vpv[3 * j - 8] = x2;
  }
}

template <int ROT>
__device__ __forceinline__ void pack_qkv(const float* acc, uint32_t (&qlo)[10], uint32_t (&qhi)[10], uint32_t (&klo)[10],
                                         uint32_t (&khi)[10], uint32_t (&vlo)[10], uint32_t (&vhi)[10]) {
#pragma unroll
  for (int j = 0; j < 10; j++) {
    const int x = (j + ROT) % 10, tq = x < 8 ? x : 16 + x, tk = x < 8 ? 8 + x : 18 + x, tv = x < 8 ? 16 + x : 20 + x;
    khi[j] = pack2(acc[4 * tk + 2], acc[4 * tk + 3]);
    vhi[j] = movm(pack2(acc[4 * tv + 2], acc[4 * tv + 3]));
    qlo[j] = pack2(acc[4 * tq], acc[4 * tq + 1]);
    qhi[j] = pack2(acc[4 * tq + 2], acc[4 * tq + 3]);
    klo[j] = pack2(acc[4 * tk], acc[4 * tk + 1]);
    vlo[j] = pack2(acc[4 * tv], acc[4 * tv + 1]);
    asm volatile("" : "+r"(khi[j]), "+r"(qlo[j]), "+r"(qhi[j]), "+r"(klo[j]), "+r"(vlo[j]));
  }
}

template <int ROT> __device__ __forceinline__ void halo_send(const float* acc, uint4* ho, uint32_t tag) {
#pragma unroll
  for (int j = 0; j < 7; j++) {
    uint32_t x[3];
#pragma unroll
    for (int e = 0; e < 3; e++) {
      const int i = 3 * j + e, y = (i % 10 + ROT) % 10, tk = y < 8 ? 8 + y : 18 + y, tv = y < 8 ? 16 + y : 20 + y;
      x[e] = i < 10 ? pack2(acc[4 * tk + 2], acc[4 * tk + 3]) : i < 20 ? movm(pack2(acc[4 * tv + 2], acc[4 * tv + 3])) : 0u;
    }
    asm volatile("st.relaxed.gpu.global.v4.u32 [%0], {%1, %2, %3, %4};" ::"l"(ho + 32 * j), "r"(x[0]), "r"(x[1]), "r"(x[2]), "r"(tag) : "memory");
  }
}

__device__ __forceinline__ void attention(float* acc, uint32_t sb, int b, int par, int w, int lane, uint32_t tag, uint32_t zero) {
  const int g = lane >> 2, t = lane & 3;
  uint32_t klo[10], khi[10], vlo[10], vhi[10], qlo[10], qhi[10], kpv[10], vpv[10];
  if (HALO_FIRST && w == 3 && b < NCTA - 8) {
    uint4* ho = g_halo + (b * 2 + par) * 224 + lane;
    if (tail_first(b & 7)) halo_send<8>(acc, ho, tag);
    else halo_send<0>(acc, ho, tag);
    TSIF(par == 0, 76);
    pin<120>(acc);
  }
  if (tail_first(b & 7)) pack_qkv<8>(acc, qlo, qhi, klo, khi, vlo, vhi);
  else pack_qkv<0>(acc, qlo, qhi, klo, khi, vlo, vhi);
  const uint32_t xa = sb + OFF_KVX + (par * 3) * 2560 + lane * 16;
  if (w < 3) {
    sts128(xa + w * 2560, khi[0], khi[1], khi[2], khi[3]);
    sts128(xa + w * 2560 + 512, khi[4], khi[5], khi[6], khi[7]);
    sts128(xa + w * 2560 + 1024, khi[8], khi[9], vhi[0], vhi[1]);
    sts128(xa + w * 2560 + 1536, vhi[2], vhi[3], vhi[4], vhi[5]);
    sts128(xa + w * 2560 + 2048, vhi[6], vhi[7], vhi[8], vhi[9]);
  } else if (!HALO_FIRST && b < NCTA - 8) {
    uint4* ho = g_halo + (b * 2 + par) * 224 + lane;
#pragma unroll
    for (int j = 0; j < 7; j++) {
      const uint32_t x0 = j < 4 ? khi[3 * j] : vhi[3 * j - 10], x1 = j < 3 ? khi[3 * j + 1] : vhi[3 * j - 9];
      const uint32_t x2 = j < 3 ? khi[3 * j + 2] : j < 6 ? vhi[3 * j - 8] : 0u;
      asm volatile("st.relaxed.gpu.global.v4.u32 [%0], {%1, %2, %3, %4};" ::"l"(ho + 32 * j), "r"(x0), "r"(x1), "r"(x2), "r"(tag) : "memory");
    }
  }
  TSIF(par == 0 && w == 1, 64);
  TSIF(par == 0 && w == 3 && !HALO_FIRST, 76);
#pragma unroll
  for (int j = 0; j < 10; j++) vlo[j] = movm(vlo[j]);
  const bool far0 = 2 * t > g, far1 = 2 * t + 1 > g;
  const uint32_t mfar = (far0 ? 0x0000FFFFu : 0u) | (far1 ? 0xFFFF0000u : 0u);
  float slo[4][2], shi[4][2], lg[2][2];
  uint32_t phi[4], plo[4], qml[4], qmh[4];
#pragma unroll
  for (int h = 0; h < 4; h++) {
    const int f = h == 0 ? 0 : h == 1 ? 3 : h == 2 ? 5 : 8, hf = h < 2 ? 2 : 7;
    const bool mine = (h & 1) ? t >= 2 : t < 2;
    qml[h] = mine ? qlo[hf] : 0u;
    qmh[h] = mine ? qhi[hf] : 0u;
    float a[4] = {0.f, 0.f, 0.f, 0.f}, c[4] = {0.f, 0.f, 0.f, 0.f};
    mma16816(a, qlo[f], qhi[f], qlo[f + 1], qhi[f + 1], klo[f], klo[f + 1]);
    mma16816(c, qlo[f], qhi[f], qlo[f + 1], qhi[f + 1], khi[f], khi[f + 1]);
    mma1688(a, qml[h], qmh[h], klo[hf]);
    mma1688(c, qml[h], qmh[h], khi[hf]);
    slo[h][0] = a[0];
    slo[h][1] = a[1];
    shi[h][0] = lg[h & 1][0] = far0 ? a[2] : c[2];
    shi[h][1] = lg[h & 1][1] = far1 ? a[3] : c[3];
    if (!ATT_MERGE && (h & 1)) softmax_two(lg, phi[h - 1], phi[h]);
  }
  TSIF(par == 0 && w == 1, 65);
  if (ATT_GATE == 3 && lane == 0) mbar_arrive(sb + OFF_BAR + 8 * B_ATT2 + (phi[3] & zero));
  wg_sync(1 + par);
  TSIF(par == 0 && w == 1, 66);
  const bool nohist = (w == 0) && (b < 8);
  const uint4* hp = g_halo + ((b - 8) * 2 + par) * 224 + lane;
  uint32_t tg[7];
  if (w > 0) {
    const uint4 v0 = lds128(xa + (w - 1) * 2560), v1 = lds128(xa + (w - 1) * 2560 + 512), v2 = lds128(xa + (w - 1) * 2560 + 1024);
    const uint4 v3 = lds128(xa + (w - 1) * 2560 + 1536), v4 = lds128(xa + (w - 1) * 2560 + 2048);
    kpv[0] = v0.x; kpv[1] = v0.y; kpv[2] = v0.z; kpv[3] = v0.w; kpv[4] = v1.x; kpv[5] = v1.y; kpv[6] = v1.z; kpv[7] = v1.w;
    kpv[8] = v2.x; kpv[9] = v2.y; vpv[0] = v2.z; vpv[1] = v2.w; vpv[2] = v3.x; vpv[3] = v3.y; vpv[4] = v3.z; vpv[5] = v3.w;
    vpv[6] = v4.x; vpv[7] = v4.y; vpv[8] = v4.z; vpv[9] = v4.w;
  } else if (nohist) {
#pragma unroll
    for (int j = 0; j < 10; j++) kpv[j] = vpv[j] = 0u;
  } else {
    TSIF(par == 0, 77);
    halo_read(kpv, vpv, tg, hp);
  }
  if (w == 0 && !nohist) {
    int spins = 0;
    while (true) {
      bool ok = true;
#pragma unroll
      for (int j = 0; j < 7; j++) ok = ok && tg[j] == tag;
      if (__all_sync(0xffffffffu, ok) || ++spins > SPIN_LIMIT) break;
      halo_read(kpv, vpv, tg, hp);
    }
    TSIF(par == 0, 79);
  }
#pragma unroll
  for (int h = 0; h < 4; h++) {
    const int f = h == 0 ? 0 : h == 1 ? 3 : h == 2 ? 5 : 8, hf = h < 2 ? 2 : 7;
    float a[4] = {0.f, 0.f, 0.f, 0.f};
    mma16816(a, qlo[f], qhi[f], qlo[f + 1], qhi[f + 1], kpv[f], kpv[f + 1]);
    mma1688(a, qml[h], qmh[h], kpv[hf]);
    const float ninf = __int_as_float(0xff800000);
    lg[h & 1][0] = far0 ? (nohist ? ninf : a[0]) : slo[h][0];
    lg[h & 1][1] = far1 ? (nohist ? ninf : a[1]) : slo[h][1];
    if (h & 1) {
      softmax_two(lg, plo[h - 1], plo[h]);
      if (ATT_MERGE) {
        const float lh[2][2] = {{shi[h - 1][0], shi[h - 1][1]}, {shi[h][0], shi[h][1]}};
        softmax_two(lh, phi[h - 1], phi[h]);
      }
    }
  }
  TSIF(par == 0 && w <= 1, 67 + w);
  if (ATT_GATE == 2 && lane == 0) mbar_arrive(sb + OFF_BAR + 8 * B_ATT2 + (plo[3] & zero));
  uint32_t ov[20];
#pragma unroll
  for (int hp = 0; hp < 2; hp++) {
    const int hf = hp ? 7 : 2;
    float sh[4] = {0.f, 0.f, 0.f, 0.f}, i0 = 0.f, i1 = 0.f;
#pragma unroll
    for (int e = 0; e < 2; e++) {
      const int h = 2 * hp + e, f = h == 0 ? 0 : h == 1 ? 3 : h == 2 ? 5 : 8;
      const uint32_t a0 = plo[h] & mfar, a2 = plo[h] & ~mfar, a3 = phi[h] & mfar, c1 = phi[h] & ~mfar;
      float sum[4] = {0.f, 0.f, 0.f, 0.f};
      mma1688(sum, plo[h], phi[h], 0x3F803F80u);
      const float r0 = rcp(sum[0]), r1 = rcp(sum[2]);
#pragma unroll
      for (int j = f; j < f + 2; j++) {
        float o[4] = {0.f, 0.f, 0.f, 0.f};
        mma16816(o, a0, 0u, a2, a3, vpv[j], vlo[j]);
        mma1688(o, 0u, c1, vhi[j]);
        ov[2 * j] = pack2(o[0] * r0, o[1] * r0);
        ov[2 * j + 1] = pack2(o[2] * r1, o[3] * r1);
      }
      const bool mine = e ? g >= 4 : g < 4;
      mma16816(sh, a0, 0u, a2, a3, mine ? vpv[hf] : 0u, mine ? vlo[hf] : 0u);
      mma1688(sh, 0u, c1, mine ? vhi[hf] : 0u);
      if (e == 0 || t >= 2) {
        i0 = r0;
        i1 = r1;
      }
    }
    ov[2 * hf] = pack2(sh[0] * i0, sh[1] * i0);
    ov[2 * hf + 1] = pack2(sh[2] * i1, sh[3] * i1);
  }
  if (ATT_GATE == 4 && lane == 0) mbar_arrive(sb + OFF_BAR + 8 * B_ATT2 + (ov[19] & zero));
  TS(32 + 4 * par + w);
  mbar_wait(sb + OFF_BAR + 8 * B_P1, 0);
  const uint32_t oa = sb + OFF_OA + (lane >> 4) * 2048 + (32 * w + 2 * (lane & 15) + par) * 16;
#pragma unroll
  for (int j = 0; j < 5; j++) stsm4(oa + 4096 * j, ov + 4 * j);
  TSIF(par == 0 && w == 0, 120);
  fence_async_smem();
  TSIF(par == 0 && w == 0, 121);
  __syncwarp();
  if (lane == 0) mbar_arrive(sb + OFF_BAR + 8 * B_ATTN);
  TSM(w == 0 || w == 2, 122 + par + (w == 2 ? 3 : 0));
}

struct Maps {
  CUtensorMap x, wm, wt, k, v, y, wo, qm, qt, om, ot, u;
};

__device__ __forceinline__ void load_stage(uint32_t sb, int kb, int b, const Maps& m) {
  const uint32_t st = sb + (kb & 3) * STAGE_BYTES, bar = sb + OFF_BAR + 8 * (B_FULL1 + (kb & 3));
  const int r = b >> 3, hg = b & 7, slab = kb - KV_KB;
  const bool kv = slab >= 0 && slab < 5;
  const uint32_t kbar = sb + OFF_BAR + 8 * (B_KV + slab), dst = sb + OFF_KVS + slab * KVS_BYTES;
  mbar_expect_tx(bar, STAGE_BYTES);
  if (kv) mbar_expect_tx(kbar, KVS_BYTES);
  tma_3d(st, &m.x, 64 * kb, 64 * r, 0, bar);
  if (kv && KV_MIX) tma_3d(dst, &m.k, 0, 32 * (b >> 1) - 3, 2 * slab + (b & 1), kbar);
  tma_3d(st + ST_W, &m.wm, 80 * hg + (tail_first(hg) ? 16 : 0), 64 * kb, 0, bar);
  if (kv && KV_MIX) tma_3d(dst + KVS_V, &m.v, 0, 32 * (b >> 1), 2 * slab + (b & 1), kbar);
  tma_3d(st + ST_WT, &m.wt, 80 * hg + (tail_first(hg) ? 0 : 64), 64 * kb, 0, bar);
  if (kv && !KV_MIX) tma_3d(dst, &m.k, 0, 32 * (b >> 1) - 3, 2 * slab + (b & 1), kbar);
  if (kv && !KV_MIX) tma_3d(dst + KVS_V, &m.v, 0, 32 * (b >> 1), 2 * slab + (b & 1), kbar);
}

__global__ void __launch_bounds__(NTHR, 1) fused_kernel(const __grid_constant__ Maps m, const Params p) {
  extern __shared__ __align__(1024) uint8_t smem[];
  const uint32_t sb = (uint32_t)__cvta_generic_to_shared(smem);
  const uint32_t bars = sb + OFF_BAR;
  const int tid = threadIdx.x, lane = tid & 31;
  int b = blockIdx.x;
  if (BMAP == 1) b = (((b & 63) >> 3) * 2 + (b & 1)) * 8 + (((b < 64 ? 0x6521 : 0x7430) >> (4 * ((b >> 1) & 3))) & 7);
  if (BMAP == 2) b = ((b & 63) >> 2) * 8 + (((b < 64 ? 0x6521 : 0x7430) >> (4 * (b & 3))) & 7);
  if (BMAP == 3) b = (((b & 63) >> 3) * 2 + (b & 1)) * 8 + (((b < 64 ? 0x7430 : 0x6521) >> (4 * ((b >> 1) & 3))) & 7);
  if (BMAP == 4) b = (((b >> 4) * 2 + (b & 1)) * 8) + ((b >> 1) & 7);
  if (BMAP == 5) b = 127 - b;
  const int r = b >> 3, hg = b & 7;

  if (tid == T_ISSUE) {
    TSM(true, 0);
#pragma unroll
    for (int i = 0; i < 4; i++) mbar_init(bars + 8 * (B_FULL1 + i), 1);
#pragma unroll
    for (int i = 0; i < 3; i++) mbar_init(bars + 8 * (B_KV + i), 1);
    fence_async_smem();
#pragma unroll 1
    for (int kb = 0; kb <= PRE2; kb++) load_stage(sb, kb, b, m);
  } else if (tid >= T_PF && tid < T_PF + 12) {
    tm_prefetch(&m.x + (tid - T_PF));
  } else if (tid == T_INIT) {
#pragma unroll
    for (int i = 0; i < 4; i++) mbar_init(bars + 8 * (B_EMPTY1 + i), 8);
#pragma unroll
    for (int i = 0; i < 8; i++) mbar_init(bars + 8 * (B_FULL2 + i), 1);
#pragma unroll
    for (int i = 0; i < 4; i++) mbar_init(bars + 8 * (B_EMPTY2 + i), 8);
#pragma unroll
    for (int i = 0; i < 4; i++) mbar_init(bars + 8 * (B_U + i), 1);
    mbar_init(bars + 8 * B_HA, 4);
    mbar_init(bars + 8 * B_GATE, 4);
    mbar_init(bars + 8 * B_HB, 1);
    mbar_init(bars + 8 * B_KVD, 4);
    mbar_init(bars + 8 * B_QF, 1);
    mbar_init(bars + 8 * B_ATTN, 8);
    mbar_init(bars + 8 * B_ATT2, 8);
    mbar_init(bars + 8 * B_P1, 8);
    mbar_init(bars + 8 * B_C34, 1);
    mbar_init(bars + 8 * B_YRB, 1);
#pragma unroll
    for (int i = 0; i < 5; i++) mbar_init(bars + 8 * (B_YST + i), 4);
#pragma unroll
    for (int i = 0; i < 5; i++) mbar_init(bars + 8 * (B_US + i), U_TMA ? 4 : i == 2 ? 20 : 1);
    mbar_init(bars + 8 * B_YSIG, 1);
    mbar_init(bars + 8 * B_YFULL, 1);
    mbar_init(bars + 8 * B_EPOCH, 1);
    mbar_init(bars + 8 * B_PREP, 4);
    mbar_init(bars + 8 * B_USIG, 1);
    mbar_init(bars + 8 * B_WST, 1);
#pragma unroll
    for (int i = 3; i < 5; i++) mbar_init(bars + 8 * (B_KV + i), 1);
    mbar_init(bars + 8 * B_E3, 8);
    mbar_init(bars + 8 * B_LAST, 1);
    mbar_init(bars + 8 * B_OSIG, 1);
    mbar_init(bars + 8 * B_WOP, 1);
    fence_async_smem();
  }
  const int warp = __shfl_sync(0xffffffffu, tid >> 5, 0), wg = warp >> 2, w = warp & 3;
  __syncthreads();

  if (wg == 3) {
    asm volatile("setmaxnreg.dec.sync.aligned.u32 56;");
    if (w == 0) {
      if (lane == 0) {
#pragma unroll 1
        for (int kb = 1 + PRE2; kb < 10; kb++) {
          if (kb >= 4) mbar_wait(bars + 8 * (kb == 7 ? B_E3 : B_EMPTY1 + (kb & 3)), (kb >> 3) & 1);
          TSIF(kb >= 4, 44 + kb);
          load_stage(sb, kb, b, m);
          TSIF(kb == 3, 60);
          if (kb == TRIG_KB) mbar_arrive(bars + 8 * B_LAST);
        }
        mbar_wait(bars + 8 * B_WOP, 0);
        mbar_wait(bars + 8 * WL_TRIG, 0);
        mbar_wait(bars + 8 * B_EPOCH, 0);
        flag_wait(g_cnt + C_W + 32 * hg, (lds32(sb + OFF_EPOCH) + 1) * 16);
        TS(30);
#pragma unroll 1
        for (int j = 0; j < 8; j++) {
          if (j >= 6) mbar_wait(bars + 8 * (B_EMPTY2 + j - 6), 0);
          if (j == 4) mbar_wait(bars + 8 * B_ATTN, 0);
          TSIF(j >= 6, 100 + j);
          if (RF_GATE && j == 6) mbar_wait(bars + 8 * B_YSIG, 0);
          mbar_expect_tx(bars + 8 * (B_FULL2 + j), j == 0 ? WO_BYTES : j == 5 ? O_BYTES + WO_BYTES + 512 : O_BYTES + WO_BYTES);
          bulk_load(sb + off_w(j), g_WO + (hg * 8 + step_src(hg, j)) * 800, WO_BYTES, bars + 8 * (B_FULL2 + j));
        }
        mbar_wait(bars + 8 * (B_EMPTY2 + Q_SLOT), 0);
        mbar_expect_tx(bars + 8 * B_QF, O_BYTES);
        tma_2d(sb + OFF_QS, &m.qm, 80 * hg, 128 * r, bars + 8 * B_QF);
        if (!QBOX) tma_2d(sb + OFF_QT, &m.qt, 80 * hg + 64, 128 * r, bars + 8 * B_QF);
      }
    } else if (w == 1) {
      unsigned epoch = 0;
      if (lane == 0) {
        epoch = atomicAdd(g_cnt + C_LAUNCH, 1u) / NCTA;
        asm volatile("st.shared.u32 [%0], %1;" ::"r"(sb + OFF_EPOCH), "r"(epoch) : "memory");
        mbar_arrive(bars + 8 * B_EPOCH);
        mbar_wait(bars + 8 * B_KVD, 0);
        mbar_expect_tx(bars + 8 * B_HB, 5 * 4096);
#pragma unroll 1
        for (int c = 0; c < 5; c++) {
          if (c == 3) mbar_wait(bars + 8 * B_S3, 0);
          bulk_load(sb + off_ch(c) + U_BYTES, p.ssm_k + (5 * b + c) * SEQ, 4096, bars + 8 * B_HB);
        }
#pragma unroll
        for (int c = 0; c < 4; c++) mbar_expect_tx(bars + 8 * (B_U + c), c < 3 ? U_BYTES : 2 * U_BYTES);
        const uint4* usrc = g_U + 5 * b * U_PITCH;
        mbar_wait(bars + 8 * B_USIG, 0);
        flag_wait(g_cnt + C_PREP + 32 * (b & 15), (epoch + 1) * NCTA);
        TS(23);
#pragma unroll
        for (int c = 0; c < 5; c++) {
          if (c == 3 && U_TRIM) mbar_wait(bars + 8 * (B_U + 2), 0);
          bulk_load(sb + off_ch(c), usrc + c * U_PITCH, U_BYTES, bars + 8 * (B_U + (c < 3 ? c : 3)));
          TSIF(c == 0 || c == 4, 116 + (c >> 2));
        }
      }
      epoch = __shfl_sync(0xffffffffu, epoch, 0);
      if (lane < 8) {
        const int src = (b & ~7) | step_src(hg, lane);
        mbar_wait(bars + 8 * OP_TRIG, 0);
        TS(20);
        bool seen = false;
#pragma unroll 1
        for (int spins = 0; spins < SPIN_LIMIT; spins++) {
          const bool now = !seen && (int)(flag_read(g_cnt + C_O + 32 * src) - (epoch + 1)) >= 0;
          if (now && lane >= 1 && lane < 4) bulk_load(sb + off_o(lane), g_O + src * 1280, O_BYTES, bars + 8 * (B_FULL2 + lane));
          seen = seen || now;
          if (__all_sync(0xff, seen)) break;
        }
        TS(21);
        if (lane == 5) bulk_load(sb + OFF_GATE, g_gate + 128 * r, 512, bars + 8 * (B_FULL2 + 5));
#pragma unroll 1
        for (int j = 4; j < 8; j++) {
          if (lane == j) {
            mbar_wait(bars + 8 * (j < 6 ? B_C34 : B_EMPTY2 + j - 6), 0);
            if (RF_GATE && j == 6) mbar_wait(bars + 8 * B_YSIG, 0);
            bulk_load(sb + off_o(j), g_O + src * 1280, O_BYTES, bars + 8 * (B_FULL2 + j));
          }
          __syncwarp(0xff);
        }
        TS(22);
      }
    } else if (w == 2) {
      mbar_wait(bars + 8 * B_PREP, 0);
      flag_signal(g_cnt + C_PREP, 16, lane);
      TS(25);
      if (lane == 0) {
        mbar_arrive(bars + 8 * B_USIG);
        mbar_expect_tx(bars + 8 * B_ORB, O_BYTES + 64);
        mbar_wait(bars + 8 * B_GATE, 0);
        bulk_store(g_gate + 16 * b, sb + OFF_GATE + 64 * hg, 64);
        bulk_wait_read<0>();
        bulk_load(sb + OFF_GATE + 64 * hg, g_gate + 16 * b, 64, bars + 8 * B_ORB);
        mbar_wait(bars + 8 * B_ATTN, 0);
        constexpr uint32_t PB = O_BYTES / O_SPLIT;
#pragma unroll
        for (int i = 0; i < O_SPLIT; i++) bulk_store(g_O + b * 1280 + i * (PB / 16), sb + OFF_OA + i * PB, PB);
#pragma unroll
        for (int i = 0; i < O_SPLIT; i++) {
          if (O_SPLIT - 1 - i == 4) bulk_wait_read<4>();
          if (O_SPLIT - 1 - i == 3) bulk_wait_read<3>();
          if (O_SPLIT - 1 - i == 2) bulk_wait_read<2>();
          if (O_SPLIT - 1 - i == 1) bulk_wait_read<1>();
          if (O_SPLIT - 1 - i == 0) bulk_wait_read<0>();
          bulk_load(sb + OFF_OA + i * PB, g_O + b * 1280 + i * (PB / 16), PB, bars + 8 * B_ORB);
        }
        TS(74);
        mbar_wait(bars + 8 * B_ORB, 0);
        flag_bump(g_cnt + C_O + 32 * b);
        TS(26);
        mbar_arrive(bars + 8 * B_OSIG);
      }
    } else {
      if (lane == 0) {
        uint4* dst = g_WO + (hg * 8 + (r >> 1)) * 800 + (r & 1) * 80;
        if (WPF) {
          mbar_wait(bars + 8 * WPF, 0);
          if (WPF_LIN)
            asm volatile("cp.async.bulk.prefetch.L2.global [%0], 6400;" ::"l"(p.wo + b * 3200) : "memory");
          else
            asm volatile("cp.async.bulk.prefetch.tensor.3d.L2.global [%0, {%1, %2, %3}];" ::"l"(&m.wo), "r"(0), "r"(40 * r), "r"(5 * hg) : "memory");
        }
        mbar_wait(bars + 8 * B_P1, 0);
        mbar_wait(bars + 8 * WB_TRIG, 0);
        mbar_expect_tx(bars + 8 * B_WST, WO_BYTES / 2);
        tma_3d(sb + OFF_WS, &m.wo, 0, 40 * r, 5 * hg, bars + 8 * B_WST);
        mbar_wait(bars + 8 * B_WST, 0);
        mbar_wait(bars + 8 * WO_TRIG, 0);
#pragma unroll 1
        for (int n = 0; n < 5; n++)
          asm volatile("cp.async.bulk.global.shared::cta.bulk_group [%0], [%1], 1280;" ::"l"(dst + 160 * n), "r"(sb + OFF_WS + 1280 * n) : "memory");
        if (W_RB) {
          asm volatile("cp.async.bulk.commit_group;\ncp.async.bulk.wait_group.read 0;" ::: "memory");
          mbar_expect_tx(bars + 8 * B_WST, WO_BYTES / 2);
#pragma unroll 1
          for (int n = 0; n < 5; n++) bulk_load(sb + OFF_WS + 1280 * n, dst + 160 * n, 1280, bars + 8 * B_WST);
          mbar_wait(bars + 8 * B_WST, 1);
        } else {
          asm volatile("cp.async.bulk.commit_group;\ncp.async.bulk.wait_group 0;\nfence.proxy.async.global;" ::: "memory");
          if (!(NOMB & 4)) asm volatile("fence.release.gpu;" ::: "memory");
        }
        flag_bump(g_cnt + C_W + 32 * hg);
        mbar_arrive(bars + 8 * B_WOP);
        TS(71);
        mbar_expect_tx(bars + 8 * B_C34, 3 * U_BYTES);
        mbar_expect_tx(bars + 8 * B_YRB, 2 * U_BYTES);
#pragma unroll 1
        for (int c = 0; c < 5; c++) {
          mbar_wait(bars + 8 * (B_YST + c), 0);
          asm volatile("cp.async.bulk.global.shared::cta.bulk_group [%0], [%1], 4096;\ncp.async.bulk.commit_group;\n"
                       "cp.async.bulk.wait_group.read 0;" ::"l"(g_Y + (5 * b + c) * Y_PITCH), "r"(sb + off_ch(c)) : "memory");
          bulk_load(sb + off_ch(c), g_Y + (5 * b + c) * Y_PITCH, U_BYTES, bars + 8 * (c < 3 ? B_C34 : B_YRB));
        }
        TS(75);
        mbar_wait(bars + 8 * B_C34, 0);
        mbar_wait(bars + 8 * B_YRB, 0);
        flag_bump(g_cnt + C_Y + 32 * (b >> 4));
        TS(27);
        mbar_arrive(bars + 8 * B_YSIG);
        mbar_expect_tx(bars + 8 * B_YFULL, 20480);
        flag_wait(g_cnt + C_Y + 32 * hg, (lds32(sb + OFF_EPOCH) + 1) * 16);
        TS(24);
        tma_2d(sb + OFF_YT, &m.y, 128 * r, 80 * hg, bars + 8 * B_YFULL);
        tma_2d(sb + OFF_YT + 10240, &m.y, 128 * r + 64, 80 * hg, bars + 8 * B_YFULL);
      }
    }
  } else {
    asm volatile("setmaxnreg.inc.sync.aligned.u32 152;");
    if (wg < 2) {
      float acc[120];
#pragma unroll
      for (int i = 0; i < 120; i++) acc[i] = 0.f;
      const uint32_t da = desc_lo(sb + wg * 8192, 16), db = desc_lo(sb + ST_W, 8192), dc = desc_lo(sb + ST_WT, 2048);
      if (PW1) pin<120>(acc);
      if (PW1 == 2) mbar_wait(bars + 8 * B_FULL1, 0);
#pragma unroll 1
      for (int kb = 0; kb < 10; kb++) {
        mbar_wait(bars + 8 * (B_FULL1 + (kb & 3)), (kb >> 2) & 1);
        const uint32_t so = (kb & 3) * (STAGE_BYTES >> 4);
        wg_fence();
#pragma unroll
        for (int k = 0; k < 4; k++) {
          WgSST<192>::mma<HI_SW128, HI_SW128>(acc, da + so + 2 * k, db + so + 128 * k, 1);
          WgSST<48>::mma<HI_SW128, HI_SW32>(acc + 96, da + so + 2 * k, dc + so + 32 * k, 1);
        }
        wg_commit();
        wg_wait<1>();
        if (kb > 0 && lane == 0) mbar_arrive(bars + 8 * (kb == 4 ? B_E3 : B_EMPTY1 + ((kb - 1) & 3)));
      }
      mbar_wait(bars + 8 * B_EPOCH, 0);
      const uint32_t tag = lds32(sb + OFF_EPOCH) + 1;
      mbar_wait(bars + 8 * B_S3, 0);
      wg_wait<0>();
      pin<120>(acc);
      if (lane == 0) mbar_arrive(bars + 8 * B_P1);
      TSM(w == 0, 3 + wg);
      attention(acc, sb, b, wg, w, lane, tag, p.zero);
    } else {
      const int tw = tid & 127, chl = 64 * (b & 1) + 8 * w + (lane >> 2);
      uint4* up = g_U + chl * U_PITCH + ((4 * (b >> 1) + (lane & 3)) ^ ((b >> 2) & 1));
      uint2 sw[10];
      uint32_t dv = 0;
      if (lane < 5) dv = __ldg(reinterpret_cast<const unsigned short*>(p.ssm_D) + 5 * b + lane);
#pragma unroll
      for (int i = 0; i < 10; i++) sw[i] = ldg64(reinterpret_cast<const uint2*>(p.shift_k) + chl + 128 * (i >> 1) + 32 * (i & 1));
      uint32_t tab[12];
      uint32_t tt[2];
      fft_tables(tab, tw);
      fft_twiddles(tt, tw);
      uint4 res[10];
#pragma unroll
      for (int i = 0; i < 10; i++) res[i] = make_uint4(0, 0, 0, 0);
#pragma unroll 1
      for (int slab = 0; slab < 5; slab++) {
#pragma unroll
        for (int i = 0; i < 8; i++) res[i] = res[i + 2];
        prep_slab(res + 8, sw, sb, slab, w, lane);
        TSIF(w == 0, 99 + 4 * slab);
#pragma unroll
        for (int i = 0; i < 8; i++) sw[i] = sw[i + 2];
      }
      TSIF(w == 0, 28);
      __syncwarp();
      if (lane == 0) mbar_arrive(bars + 8 * B_KVD + ((res[8].x ^ res[9].x) & p.zero));
      mbar_wait(bars + 8 * B_KVD, 0);
      fft_tables_store(tab, sb, tw);
      mbar_wait(bars + 8 * B_LAST, 0);
#pragma unroll
      for (int i = 0; i < 10; i++) up[(128 * (i >> 1) + 32 * (i & 1)) * U_PITCH] = res[i];
      __syncwarp();
      if (lane == 0) mbar_arrive(bars + 8 * B_PREP);
      TSIF(w == 0 && !U_TMA, 5);
      mbar_wait(bars + 8 * (G_AFTER ? B_USIG : B_LAST), 0);
      prep_gate(p, sb, b, w, lane);
      __syncwarp();
      if (lane == 0) mbar_arrive(bars + 8 * B_GATE);
      TSIF(w == 0, 72);
      mbar_wait(bars + 8 * B_HB, 0);
      TSIF(w == 0, 2);
      const uint32_t ha = sb + U_BYTES + ((tw >> 3) * 16 + 8 + (tw & 7)) * 16;
      uint4 hv[5];
#pragma unroll
      for (int c = 0; c < 5; c++) hv[c] = lds128(ha + off_ch(c));
      __syncwarp();
#pragma unroll
      for (int c = 0; c < 5; c++) sts128((ha ^ 16) + off_ch(c), hv[c].x, hv[c].y, hv[c].z, hv[c].w);
      asm volatile("st.shared.v2.u32 [%0], {%1, %2};" ::"r"(sb + OFF_TT + 8 * tw), "r"(tt[0]), "r"(tt[1]) : "memory");
      if (tw < 5) asm volatile("st.shared.f32 [%0], %1;" ::"r"(sb + OFF_D + 4 * tw), "f"(bf_lo(dv) * 0.125f) : "memory");
      fence_async_smem();
      __syncwarp();
      if (lane == 0) mbar_arrive(bars + 8 * B_HA);
      TSIF(w == 0, 6);
    }

    FftConst fc;
    TSM(w == 0 && wg == 0, 104);
    mbar_wait(bars + 8 * B_HA, 0);
    fft_matrices(fc, sb, w, lane);
    TSM(w == 0 && wg == 0, 105);
    TSM(w == 0 && wg == 2, 124);
    uint32_t tasks = wg == 0 ? TASK0 : wg == 1 ? TASK1 : TASK2, fa[4][4];
    {
      float X[32];
      wg_fence();
      f_step(X, fc, desc_lo(sb + off_ch((tasks & 7) - 1) + U_BYTES, 1024));
      wg_wait<0>();
      pin<32>(X);
      twiddle_fwd(fa, X, fc);
    }
#pragma unroll 1
    for (; tasks; tasks >>= 4) {
      const int c = (tasks & 7) - 1;
      conv_channel(fc, fa, sb, c, ((tasks >> 4) & 7) - 1, wg, w, lane);
      if (lane == 0) mbar_arrive(bars + 8 * (B_YST + c));
      TSM(w == 0, 10 + c);
    }

    if (wg < 2) {
      const int g = lane >> 2;
      float acc[40];
#pragma unroll
      for (int i = 0; i < 40; i++) acc[i] = 0.f;
      const uint32_t da = desc_lo(sb + wg * 1024, 2048), db = desc_lo(sb, 2560);
      mbar_wait(bars + 8 * (O_RB == 2 ? B_ORB : B_ATTN), 0);
      if (PW2) mbar_wait(bars + 8 * B_FULL2, 0);
      mbar_wait(bars + 8 * B_CVD, 0);
      TSM(w == 0, 15 + wg);
#pragma unroll 1
      for (int j = 0; j < 8; j++) {
        mbar_wait(bars + 8 * (B_FULL2 + j), 0);
        TSM(w == 0 && wg == 0, 44 + (j < 4 ? j : j + 6));
        const uint32_t oa = da + (off_o(j) >> 4), ob = db + (off_w(j) >> 4);
        wg_fence();
#pragma unroll
        for (int k = 0; k < 5; k++) WgSST<80>::mma<HI_NONE, HI_SW32>(acc, oa + 256 * k, ob + 32 * k, 1);
        wg_commit();
        wg_wait<1>();
        if (j >= 1 && j <= Q_SLOT + 1 && lane == 0) mbar_arrive(bars + 8 * (B_EMPTY2 + j - 1));
      }
      TSIF(w == 0 && wg == 0, 113);
      const int tr = 64 * wg + 16 * w + (lane & 15);
      const uint32_t fm = sb + OFF_QS + tr * 128, fx = (lane >> 4) ^ (tr & 7), fq = sb + OFF_QS + tr * 160 + (lane >> 4) * 16;
      const uint32_t ft = sb + OFF_QT + tr * 32 + (((lane >> 4) ^ (tr >> 2)) & 1) * 16;
      const float g0 = __uint_as_float(lds32(sb + OFF_GATE + (64 * wg + 16 * w + g) * 4));
      const float g1 = __uint_as_float(lds32(sb + OFF_GATE + (64 * wg + 16 * w + 8 + g) * 4));
      const uint32_t ga = pack2(g0, g0), gb = pack2(g1, g1);
      const uint32_t na = pack2(1.f - g0, 1.f - g0), nb = pack2(1.f - g1, 1.f - g1);

      uint32_t qf[20];
      mbar_wait(bars + 8 * B_QF, 0);
      TSM(w == 0 && wg == 0, 99);
#pragma unroll
      for (int j = 0; j < 5; j++) ldsm4(qf + 4 * j, QBOX ? fq + 32 * j : j < 4 ? fm + ((fx ^ (2 * j)) << 4) : ft);
      if (FUSE_MIX) {
#pragma unroll
        for (int i = 0; i < 20; i++) {
          qf[i] = bmul((i & 1) ? gb : ga, qf[i]);
          asm volatile("" : "+r"(qf[i]));
        }
      }
      wg_wait<0>();
      pin<40>(acc);
      TSM(w == 0, 17 + wg);
      uint32_t pb[20];
#pragma unroll
      for (int j = 0; j < 10; j++) {
        pb[2 * j] = bmul(na, pack2(acc[4 * j], acc[4 * j + 1]));
        pb[2 * j + 1] = bmul(nb, pack2(acc[4 * j + 2], acc[4 * j + 3]));
        asm volatile("" : "+r"(pb[2 * j]), "+r"(pb[2 * j + 1]));
      }
      const uint32_t ya = sb + OFF_YT + wg * 10240 + ((lane >> 4) * 8 + (lane & 7)) * 128 +
                          (((2 * w + (((lane >> 3) & 1) ^ wg)) ^ (lane & 7)) << 4);
      mbar_wait(bars + 8 * B_YFULL, 0);
      TSM(w == 0 && wg == 0, 19);
#pragma unroll
      for (int j = 0; j < 5; j++) {
        uint32_t y[4];
        ldsm4t(y, ya + 2048 * j);
#pragma unroll
        for (int i = 0; i < 4; i++)
          qf[4 * j + i] = FUSE_MIX ? bfma(qf[4 * j + i], y[i], pb[4 * j + i]) : badd(bmul((i & 1) ? gb : ga, bmul(qf[4 * j + i], y[i])), pb[4 * j + i]);
      }
#pragma unroll
      for (int j = 0; j < 5; j++) stsm4(QBOX ? fq + 32 * j : j < 4 ? fm + ((fx ^ (2 * j)) << 4) : ft, qf + 4 * j);
      fence_async_smem();
      __syncwarp();
      if (lane == 0) {
        const int row = 64 * wg + 16 * w;
        asm volatile("cp.async.bulk.tensor.2d.global.shared::cta.bulk_group [%0, {%2, %3}], [%1];"
                     ::"l"(&m.om), "r"(sb + OFF_QS + row * (QBOX ? 160 : 128)), "r"(80 * hg), "r"(128 * r + row) : "memory");
        if (!QBOX) asm volatile("cp.async.bulk.tensor.2d.global.shared::cta.bulk_group [%0, {%2, %3}], [%1];"
                     ::"l"(&m.ot), "r"(sb + OFF_QT + row * 32), "r"(80 * hg + 64), "r"(128 * r + row) : "memory");
        asm volatile("cp.async.bulk.commit_group;\ncp.async.bulk.wait_group.read 0;" ::: "memory");
      }
      TSM(w == 0 || w == 3, 40 + 2 * wg + (w & 1));
      if (ENDBAR) asm volatile("bar.sync 15, 256;" ::: "memory");
    }
  }
}

typedef CUresult (*EncodeFn)(CUtensorMap*, CUtensorMapDataType, cuuint32_t, void*, const cuuint64_t*, const cuuint64_t*,
                             const cuuint32_t*, const cuuint32_t*, CUtensorMapInterleave, CUtensorMapSwizzle,
                             CUtensorMapL2promotion, CUtensorMapFloatOOBfill);

void encode(EncodeFn fn, CUtensorMap* tm, const void* base, int rank, const cuuint64_t* dims, const cuuint64_t* strides,
            const cuuint32_t* box, CUtensorMapSwizzle swz) {
  const cuuint32_t ones[3] = {1, 1, 1};
  fn(tm, CU_TENSOR_MAP_DATA_TYPE_BFLOAT16, rank, const_cast<void*>(base), dims, strides, box, ones,
     CU_TENSOR_MAP_INTERLEAVE_NONE, swz, CU_TENSOR_MAP_L2_PROMOTION_L2_128B, CU_TENSOR_MAP_FLOAT_OOB_FILL_NONE);
}

}

extern "C" void kernel_launch(void* const* d_in, const int* in_sizes, int n_in, void* d_out, int out_size) {
  (void)in_sizes; (void)n_in; (void)out_size;
  Params p;
  p.q = (const __nv_bfloat16*)d_in[0];
  p.k = (const __nv_bfloat16*)d_in[1];
  p.v = (const __nv_bfloat16*)d_in[2];
  p.shift_k = (const __nv_bfloat16*)d_in[3];
  p.ssm_k = (const __nv_bfloat16*)d_in[4];
  p.ssm_D = (const __nv_bfloat16*)d_in[5];
  p.wqkv = (const __nv_bfloat16*)d_in[7];
  p.wo = (const __nv_bfloat16*)d_in[8];
  p.gate_w = (const __nv_bfloat16*)d_in[9];
  p.out = (__nv_bfloat16*)d_out;
  p.zero = 0;

  static EncodeFn fn = nullptr;
  static void *yaddr = nullptr, *uaddr = nullptr;
  if (!fn) {
    cudaDriverEntryPointQueryResult qr;
    void* f = nullptr;
    cudaGetDriverEntryPoint("cuTensorMapEncodeTiled", &f, cudaEnableDefault, &qr);
    fn = (EncodeFn)f;
    cudaGetSymbolAddress(&yaddr, g_Y);
    cudaGetSymbolAddress(&uaddr, g_U);
    cudaFuncSetAttribute(fused_kernel, cudaFuncAttributeMaxDynamicSharedMemorySize, SMEM_BYTES);
  }
  Maps m;
  {
    const cuuint64_t dims[3] = {640, 1024, 2}, st[2] = {2560, 1280};
    const cuuint32_t box[3] = {64, 64, 2};
    encode(fn, &m.x, p.q, 3, dims, st, box, CU_TENSOR_MAP_SWIZZLE_128B);
  }
  {
    const cuuint64_t dims[3] = {640, 640, 3}, st[2] = {3840, 1280};
    const cuuint32_t box[3] = {64, 64, 3}, boxt[3] = {16, 64, 3};
    encode(fn, &m.wm, p.wqkv, 3, dims, st, box, CU_TENSOR_MAP_SWIZZLE_128B);
    encode(fn, &m.wt, p.wqkv, 3, dims, st, boxt, CU_TENSOR_MAP_SWIZZLE_32B);
  }
  {
    const cuuint64_t dims[3] = {64, 2048, 10}, st[2] = {1280, 128};
    const cuuint32_t boxk[3] = {64, 35, 1}, boxv[3] = {64, 32, 1};
    encode(fn, &m.k, p.k, 3, dims, st, boxk, CU_TENSOR_MAP_SWIZZLE_128B);
    encode(fn, &m.v, p.v, 3, dims, st, boxv, CU_TENSOR_MAP_SWIZZLE_128B);
  }
  {
    const cuuint64_t dims[3] = {16, 640, 40}, st[2] = {1280, 32};
    const cuuint32_t box[3] = {16, 40, 5};
    encode(fn, &m.wo, p.wo, 3, dims, st, box, CU_TENSOR_MAP_SWIZZLE_32B);
  }
  {
    const cuuint64_t dims[2] = {2048, 640}, st[1] = {Y_PITCH * 16};
    const cuuint32_t box[2] = {64, 80};
    encode(fn, &m.y, yaddr, 2, dims, st, box, CU_TENSOR_MAP_SWIZZLE_128B);
    const cuuint64_t stu[1] = {U_PITCH * 16};
    const cuuint32_t boxu[2] = {32, 64};
    encode(fn, &m.u, uaddr, 2, dims, stu, boxu, CU_TENSOR_MAP_SWIZZLE_NONE);
  }
  {
    const cuuint64_t dims[2] = {640, 2048}, st[1] = {1280};
    const cuuint32_t bqm[2] = {QBOX ? 80 : 64, 128}, bqt[2] = {16, 128}, bom[2] = {QBOX ? 80 : 64, 16}, bot[2] = {16, 16};
    encode(fn, &m.qm, p.q, 2, dims, st, bqm, QBOX ? CU_TENSOR_MAP_SWIZZLE_NONE : CU_TENSOR_MAP_SWIZZLE_128B);
    encode(fn, &m.qt, p.q, 2, dims, st, bqt, CU_TENSOR_MAP_SWIZZLE_32B);
    encode(fn, &m.om, p.out, 2, dims, st, bom, QBOX ? CU_TENSOR_MAP_SWIZZLE_NONE : CU_TENSOR_MAP_SWIZZLE_128B);
    encode(fn, &m.ot, p.out, 2, dims, st, bot, CU_TENSOR_MAP_SWIZZLE_32B);
  }
  fused_kernel<<<NCTA, NTHR, SMEM_BYTES>>>(m, p);
}
```

```cpp
#include <cuda.h>
#include <cuda_bf16.h>
#include <cuda_runtime.h>
#include <stdint.h>

namespace {

constexpr int SEQ = 2048, DIM = 640, NCTA = 128, NTHR = 512;

#define TRIG_KB 9
#define KV_KB 2
#define DEV_EXIT 0
#define ATT_GATE 0
#define G_AFTER 0
#define FENCE_LO 0
#define FENCE_HI 0
#define PW1 2
#define PW2 1
#define ENDBAR 0
#define PAD_KB 0
#define Y_ALIAS 1
#define NOMB 0
#define SRC_ROT 0
#define WAIT_NS 0
#define WB_TRIG B_USIG
#define G_POS 0
#define TAILF 1
#define T_ISSUE 384
#define T_PF 416
#define T_INIT 448
#define ATT_MERGE 0
#define BMAP 1
#define PRE2 1
#define KV_MIX 0
#define O_DEFER 0
#define TASK0 0x3
#define TASK1 0x52
#define TASK2 0x41
#define HALO_FIRST 1
#define PREV_EARLY 0
#define Y_RB 2
#define O_RB 2
#define O_EAGER 1
#define OP_TRIG B_ATTN
#define FUSE_MIX 1
#define Q_EARLY 1
#define U_TRIM 1
#define Q_SLOT 3
#define G_TMA 1
#define W_RB 1
#define WPF B_S3
#define WPF_LIN 1
#define QBOX 0
#define O_SPLIT 1
#define WO_SKIP 1
#define ACQ 0
#define U_TMA 0
#define U_GATE 0
#define RF_GATE 0
#define WO_TRIG B_WST
#define WL_TRIG B_WOP
#define WO_GATE 4

constexpr uint32_t STAGE_BYTES = 47104, ST_W = 16384, ST_WT = 40960;
constexpr uint32_t O_BYTES = 20480, WO_BYTES = 12800;
constexpr uint32_t OFF_OA = 0;
constexpr uint32_t OFF_QS = Q_SLOT * O_BYTES, OFF_QT = OFF_QS + 16384;
constexpr uint32_t OFF_WC = 81920;
constexpr uint32_t OFF_WA = 94720;
constexpr uint32_t OFF_GATE = 145920;
constexpr uint32_t OFF_TT = 146432;
constexpr uint32_t OFF_KVX = 148480;
constexpr uint32_t OFF_CH3 = 163840;
constexpr uint32_t CH_BYTES = 12288, U_BYTES = 4096;
constexpr uint32_t OFF_FT = 225280, OFF_GT = 229376;
constexpr uint32_t OFF_CH0 = 188416;
constexpr uint32_t OFF_KVS = OFF_CH0, KVS_V = 4480, KVS_BYTES = 8576;
constexpr uint32_t OFF_WS = OFF_WA;
__device__ __forceinline__ uint32_t off_us(int s) { return OFF_CH0 + 4096 * ((0x65320 >> (4 * s)) & 7); }
constexpr uint32_t OFF_YT = 163840;
constexpr uint32_t OFF_BAR = 231936;
constexpr uint32_t SMEM_BYTES = OFF_BAR + 512;

enum : uint32_t {
  B_FULL1 = 0, B_EMPTY1 = 4, B_S3 = 7, B_FULL2 = 52, B_EMPTY2 = 13, B_U = 8, B_GATE = 12, B_HA = 19, B_HB = 20,
  B_ATTN = 21, B_C34 = 22, B_YRB = 23, B_YFULL = 24, B_EPOCH = 25, B_PREP = 26, B_P1 = 27, B_LAST = 28,
  B_E3 = 29, B_OSIG = 30, B_WOP = 31, B_USIG = 32, B_WST = 33, B_KV = 34, B_KVD = 39, B_QF = 17, B_ATT2 = 18, B_YST = 40,
  B_ORB = 45, B_CVD = 33 + 14, B_US = 45, B_YSIG = 50
};
constexpr uint32_t OFF_EPOCH = OFF_BAR + 8 * 51, OFF_D = OFF_BAR + 8 * 60;
__device__ __forceinline__ uint32_t off_o(int j) { return j < 4 ? OFF_OA + j * O_BYTES : j < 6 ? OFF_CH0 + (j - 4) * O_BYTES : OFF_OA + (j - 6) * O_BYTES; }
__device__ __forceinline__ uint32_t off_w(int j) { return j < 4 ? OFF_WA + j * WO_BYTES : j == 4 ? OFF_KVX : j == 5 ? OFF_WC : OFF_WA + (j - 6) * WO_BYTES; }
__device__ __forceinline__ int step_src(int hg, int j) {
  if (SRC_ROT == 2) {
    const int pos = (0x37621540 >> (4 * hg)) & 7;
    return j == 0 ? hg : (0x65217430 >> (4 * (j <= pos ? j - 1 : j))) & 7;
  }
  return SRC_ROT ? (hg + j) & 7 : j == 0 ? hg : j <= hg ? j - 1 : j;
}
__device__ __forceinline__ bool tail_first(int hg) { return TAILF && (hg & 3) == 3; }
__device__ __forceinline__ uint32_t off_ch(int c) { return (c < 3 ? OFF_CH0 : OFF_CH3 - 3 * CH_BYTES) + c * CH_BYTES; }

#define U_PITCH 264
__device__ __align__(1024) uint4 g_U[DIM * U_PITCH];
__device__ uint4 g_O[NCTA * 1280];
#define g_Y g_U
constexpr int Y_PITCH = U_PITCH;
__device__ uint4 g_WO[64 * 800];
__device__ uint4 g_halo[NCTA * 2 * 7 * 32];
__device__ __align__(128) float g_gate[SEQ + PAD_KB * 256];
__device__ unsigned g_cnt[32 * (1 + 2 * 16 + 8 + NCTA)];
constexpr int C_LAUNCH = 0, C_PREP = 32, C_Y = 32 * 17, C_W = 32 * 33, C_O = 32 * 41;

#define TSM(cond, slot) do { } while (0)
#define TSIF(cond, slot) do { if (__LINE__ >= FENCE_LO && __LINE__ < FENCE_HI) sched_fence(); } while (0)
__device__ __forceinline__ void sched_fence() {
  asm volatile("{\n.reg .pred p;\n.reg .u32 c;\nmov.u32 c, %%clock;\nsetp.eq.u32 p, c, 0;\n@p st.shared.u32 [%0], c;\n}"
               ::"r"(1024 + OFF_EPOCH + 4) : "memory");
}
#define TS(slot) TSIF(true, slot)

struct Params {
  const __nv_bfloat16 *q, *k, *v, *shift_k, *ssm_k, *ssm_D, *wqkv, *wo, *gate_w;
  __nv_bfloat16* out;
  uint32_t zero;
};

#define POLL_NS 0
constexpr int SPIN_LIMIT = 1 << 17;

__device__ __forceinline__ void mbar_init(uint32_t bar, uint32_t count) {
  asm volatile("mbarrier.init.shared::cta.b64 [%0], %1;" ::"r"(bar), "r"(count) : "memory");
}
__device__ __forceinline__ void mbar_expect_tx(uint32_t bar, uint32_t bytes) {
  asm volatile("mbarrier.arrive.expect_tx.shared::cta.b64 _, [%0], %1;" ::"r"(bar), "r"(bytes) : "memory");
}
__device__ __forceinline__ void mbar_arrive(uint32_t bar) {
  asm volatile("mbarrier.arrive.shared::cta.b64 _, [%0];" ::"r"(bar) : "memory");
}
__device__ __forceinline__ void mbar_wait(uint32_t bar, uint32_t parity) {
  uint32_t ok;
  int spins = 0;
  do {
    if (WAIT_NS)
      asm volatile("{\n.reg .pred p;\nmbarrier.try_wait.parity.shared::cta.b64 p, [%1], %2, %3;\nselp.b32 %0, 1, 0, p;\n}"
                   : "=r"(ok) : "r"(bar), "r"(parity), "r"(WAIT_NS) : "memory");
    else
      asm volatile("{\n.reg .pred p;\nmbarrier.try_wait.parity.shared::cta.b64 p, [%1], %2;\nselp.b32 %0, 1, 0, p;\n}"
                   : "=r"(ok) : "r"(bar), "r"(parity) : "memory");
    if (++spins > SPIN_LIMIT) break;
  } while (!ok);
}
__device__ __forceinline__ unsigned flag_read(const unsigned* p) {
  unsigned v;
  asm volatile("ld.relaxed.gpu.global.u32 %0, [%1];" : "=r"(v) : "l"(p) : "memory");
  return v;
}
__device__ __forceinline__ void flag_poll(const unsigned* p, unsigned target) {
  unsigned v;
  int spins = 0;
  do {
    if (POLL_NS && spins) __nanosleep(POLL_NS);
    asm volatile("ld.relaxed.gpu.global.u32 %0, [%1];" : "=r"(v) : "l"(p) : "memory");
    if (++spins > SPIN_LIMIT) break;
  } while ((int)(v - target) < 0);
}
__device__ __forceinline__ void flag_wait(const unsigned* p, unsigned target) {
  flag_poll(p, target);
  if (ACQ) asm volatile("fence.acquire.gpu;\nfence.proxy.async.global;" ::: "memory");
}
__device__ __forceinline__ void flag_signal(unsigned* p, int n, int lane) {
  if (lane == 0) asm volatile("fence.release.gpu;" ::: "memory");
  __syncwarp();
  if (lane < n) asm volatile("red.relaxed.gpu.global.add.u32 [%0], 1;" ::"l"(p + 32 * lane) : "memory");
}
__device__ __forceinline__ void flag_bump(unsigned* p) {
  asm volatile("red.relaxed.gpu.global.add.u32 [%0], 1;" ::"l"(p) : "memory");
}
__device__ __forceinline__ void fence_async_smem() { asm volatile("fence.proxy.async.shared::cta;" ::: "memory"); }
__device__ __forceinline__ void wg_sync(int id) { asm volatile("bar.sync %0, 128;" ::"r"(id) : "memory"); }

__device__ __forceinline__ void tma_2d(uint32_t dst, const CUtensorMap* tm, int c0, int c1, uint32_t bar) {
  asm volatile("cp.async.bulk.tensor.2d.shared::cluster.global.mbarrier::complete_tx::bytes [%0], [%1, {%3, %4}], [%2];"
               ::"r"(dst), "l"(tm), "r"(bar), "r"(c0), "r"(c1) : "memory");
}
__device__ __forceinline__ void tma_3d(uint32_t dst, const CUtensorMap* tm, int c0, int c1, int c2, uint32_t bar) {
  asm volatile("cp.async.bulk.tensor.3d.shared::cluster.global.mbarrier::complete_tx::bytes [%0], [%1, {%3, %4, %5}], [%2];"
               ::"r"(dst), "l"(tm), "r"(bar), "r"(c0), "r"(c1), "r"(c2) : "memory");
}
__device__ __forceinline__ void bulk_load(uint32_t dst, const void* src, uint32_t bytes, uint32_t bar) {
  asm volatile("cp.async.bulk.shared::cluster.global.mbarrier::complete_tx::bytes [%0], [%1], %2, [%3];"
               ::"r"(dst), "l"(src), "r"(bytes), "r"(bar) : "memory");
}
__device__ __forceinline__ void bulk_store(void* dst, uint32_t src, uint32_t bytes) {
  asm volatile("cp.async.bulk.global.shared::cta.bulk_group [%0], [%1], %2;\ncp.async.bulk.commit_group;"
               ::"l"(dst), "r"(src), "r"(bytes) : "memory");
}
template <int N> __device__ __forceinline__ void bulk_wait_read() { asm volatile("cp.async.bulk.wait_group.read %0;" ::"n"(N) : "memory"); }
__device__ __forceinline__ void tm_prefetch(const CUtensorMap* tm) {
  asm volatile("prefetch.tensormap [%0];" ::"l"(tm) : "memory");
}

__device__ __forceinline__ void wg_fence() { asm volatile("wgmma.fence.sync.aligned;" ::: "memory"); }
__device__ __forceinline__ void wg_commit() { asm volatile("wgmma.commit_group.sync.aligned;" ::: "memory"); }
template <int N> __device__ __forceinline__ void wg_wait() { asm volatile("wgmma.wait_group.sync.aligned %0;" ::"n"(N) : "memory"); }
__device__ __forceinline__ uint32_t desc_lo(uint32_t addr, uint32_t lbo) { return ((addr & 0x3FFFF) >> 4) | ((lbo >> 4) << 16); }
constexpr uint32_t desc_hi(uint32_t sbo, uint32_t swz) { return (sbo >> 4) | (swz << 30); }
constexpr uint32_t HI_SW128 = desc_hi(1024, 1), HI_SW64 = desc_hi(512, 2), HI_SW32 = desc_hi(256, 3), HI_NONE = desc_hi(128, 0);
template <int N> __device__ __forceinline__ void pin(float* d) {
#pragma unroll
  for (int i = 0; i < N; i++) asm volatile("" : "+f"(d[i])::"memory");
}

__device__ __forceinline__ uint32_t lds32(uint32_t a) {
  uint32_t v;
  asm volatile("ld.volatile.shared.u32 %0, [%1];" : "=r"(v) : "r"(a) : "memory");
  return v;
}
__device__ __forceinline__ uint4 ldg128(const void* a) {
  uint4 v;
  asm volatile("ld.global.nc.v4.u32 {%0, %1, %2, %3}, [%4];" : "=r"(v.x), "=r"(v.y), "=r"(v.z), "=r"(v.w) : "l"(a) : "memory");
  return v;
}
__device__ __forceinline__ uint2 ldg64(const void* a) {
  uint2 v;
  asm volatile("ld.global.nc.v2.u32 {%0, %1}, [%2];" : "=r"(v.x), "=r"(v.y) : "l"(a) : "memory");
  return v;
}
__device__ __forceinline__ void ldsm4(uint32_t* r, uint32_t a) {
  asm volatile("ldmatrix.sync.aligned.m8n8.x4.shared.b16 {%0, %1, %2, %3}, [%4];"
               : "=r"(r[0]), "=r"(r[1]), "=r"(r[2]), "=r"(r[3]) : "r"(a) : "memory");
}
__device__ __forceinline__ void ldsm4t(uint32_t* r, uint32_t a) {
  asm volatile("ldmatrix.sync.aligned.m8n8.x4.trans.shared.b16 {%0, %1, %2, %3}, [%4];"
               : "=r"(r[0]), "=r"(r[1]), "=r"(r[2]), "=r"(r[3]) : "r"(a) : "memory");
}
__device__ __forceinline__ uint2 lds64(uint32_t a) {
  uint2 v;
  asm volatile("ld.shared.v2.u32 {%0, %1}, [%2];" : "=r"(v.x), "=r"(v.y) : "r"(a) : "memory");
  return v;
}
__device__ __forceinline__ uint4 lds128(uint32_t a) {
  uint4 v;
  asm volatile("ld.shared.v4.u32 {%0, %1, %2, %3}, [%4];" : "=r"(v.x), "=r"(v.y), "=r"(v.z), "=r"(v.w) : "r"(a) : "memory");
  return v;
}
__device__ __forceinline__ void sts128(uint32_t a, uint32_t x, uint32_t y, uint32_t z, uint32_t w) {
  asm volatile("st.shared.v4.u32 [%0], {%1, %2, %3, %4};" ::"r"(a), "r"(x), "r"(y), "r"(z), "r"(w) : "memory");
}
__device__ __forceinline__ void stsm4(uint32_t a, const uint32_t* r) {
  asm volatile("stmatrix.sync.aligned.m8n8.x4.shared.b16 [%0], {%1, %2, %3, %4};" ::"r"(a), "r"(r[0]), "r"(r[1]), "r"(r[2]), "r"(r[3]) : "memory");
}
__device__ __forceinline__ void stsm4t(uint32_t a, const uint32_t* r) {
  asm volatile("stmatrix.sync.aligned.m8n8.x4.trans.shared.b16 [%0], {%1, %2, %3, %4};" ::"r"(a), "r"(r[0]), "r"(r[1]), "r"(r[2]), "r"(r[3]) : "memory");
}
__device__ __forceinline__ uint32_t pack2(float lo, float hi) {
  uint32_t r;
  asm("cvt.rn.bf16x2.f32 %0, %1, %2;" : "=r"(r) : "f"(hi), "f"(lo));
  return r;
}
__device__ __forceinline__ uint32_t movm(uint32_t a) {
  uint32_t d;
  asm volatile("movmatrix.sync.aligned.m8n8.trans.b16 %0, %1;" : "=r"(d) : "r"(a));
  return d;
}
__device__ __forceinline__ uint32_t bmul(uint32_t a, uint32_t b) {
  uint32_t d;
  asm("mul.rn.bf16x2 %0, %1, %2;" : "=r"(d) : "r"(a), "r"(b));
  return d;
}
__device__ __forceinline__ uint32_t badd(uint32_t a, uint32_t b) {
  uint32_t d;
  asm("add.rn.bf16x2 %0, %1, %2;" : "=r"(d) : "r"(a), "r"(b));
  return d;
}
__device__ __forceinline__ uint32_t bfma(uint32_t a, uint32_t b, uint32_t c) {
  uint32_t d;
  asm("fma.rn.bf16x2 %0, %1, %2, %3;" : "=r"(d) : "r"(a), "r"(b), "r"(c));
  return d;
}
__device__ __forceinline__ float bf_lo(uint32_t x) { return __uint_as_float(x << 16); }
__device__ __forceinline__ float bf_hi(uint32_t x) { return __uint_as_float(x & 0xFFFF0000u); }
__device__ __forceinline__ float ex2(float x) {
  float y;
  asm("ex2.approx.ftz.f32 %0, %1;" : "=f"(y) : "f"(x));
  return y;
}
__device__ __forceinline__ float rcp(float x) {
  float y;
  asm("rcp.approx.ftz.f32 %0, %1;" : "=f"(y) : "f"(x));
  return y;
}
__device__ __forceinline__ void mma16816(float* d, uint32_t a0, uint32_t a1, uint32_t a2, uint32_t a3, uint32_t b0, uint32_t b1) {
  asm volatile("mma.sync.aligned.m16n8k16.row.col.f32.bf16.bf16.f32 {%0, %1, %2, %3}, {%4, %5, %6, %7}, {%8, %9}, {%0, %1, %2, %3};"
               : "+f"(d[0]), "+f"(d[1]), "+f"(d[2]), "+f"(d[3])
               : "r"(a0), "r"(a1), "r"(a2), "r"(a3), "r"(b0), "r"(b1));
}
__device__ __forceinline__ void mma1688(float* d, uint32_t a0, uint32_t a1, uint32_t b0) {
  asm volatile("mma.sync.aligned.m16n8k8.row.col.f32.bf16.bf16.f32 {%0, %1, %2, %3}, {%4, %5}, {%6}, {%0, %1, %2, %3};"
               : "+f"(d[0]), "+f"(d[1]), "+f"(d[2]), "+f"(d[3])
               : "r"(a0), "r"(a1), "r"(b0));
}

template <int N> struct WgRS;
template <int N> struct WgSST;
template <> struct WgRS<32> {
  template <uint32_t HB>
  static __device__ __forceinline__ void mma(float* d, const uint32_t* a, uint32_t db) {
    asm volatile("{\n.reg .pred p;\n.reg .b64 db;\nsetp.ne.b32 p, %22, 0;\n"
      "mov.b64 db, {%20, %21};\n"
      "wgmma.mma_async.sync.aligned.m64n32k16.f32.bf16.bf16 {"
      "%0, %1, %2, %3, %4, %5, %6, %7, %8, %9, %10, %11, %12, %13, %14, %15"
      "}, {%16, %17, %18, %19}, db, p, 1, 1, 1;\n}\n"
      : "+f"(d[0]), "+f"(d[1]), "+f"(d[2]), "+f"(d[3]), "+f"(d[4]), "+f"(d[5]), "+f"(d[6]), "+f"(d[7]),
        "+f"(d[8]), "+f"(d[9]), "+f"(d[10]), "+f"(d[11]), "+f"(d[12]), "+f"(d[13]), "+f"(d[14]), "+f"(d[15])
      : "r"(a[0]), "r"(a[1]), "r"(a[2]), "r"(a[3]), "r"(db), "n"(HB), "n"(1));
  }
  template <uint32_t HB>
  static __device__ __forceinline__ void set(float* d, const uint32_t* a, uint32_t db) {
    asm volatile("{\n.reg .pred p;\n.reg .b64 db;\nsetp.ne.b32 p, %22, 0;\n"
      "mov.b64 db, {%20, %21};\n"
      "wgmma.mma_async.sync.aligned.m64n32k16.f32.bf16.bf16 {"
      "%0, %1, %2, %3, %4, %5, %6, %7, %8, %9, %10, %11, %12, %13, %14, %15"
      "}, {%16, %17, %18, %19}, db, p, 1, 1, 1;\n}\n"
      : "=f"(d[0]), "=f"(d[1]), "=f"(d[2]), "=f"(d[3]), "=f"(d[4]), "=f"(d[5]), "=f"(d[6]), "=f"(d[7]),
        "=f"(d[8]), "=f"(d[9]), "=f"(d[10]), "=f"(d[11]), "=f"(d[12]), "=f"(d[13]), "=f"(d[14]), "=f"(d[15])
      : "r"(a[0]), "r"(a[1]), "r"(a[2]), "r"(a[3]), "r"(db), "n"(HB), "n"(0));
  }
};
template <> struct WgRS<64> {
  template <uint32_t HB>
  static __device__ __forceinline__ void mma(float* d, const uint32_t* a, uint32_t db) {
    asm volatile("{\n.reg .pred p;\n.reg .b64 db;\nsetp.ne.b32 p, %38, 0;\n"
      "mov.b64 db, {%36, %37};\n"
      "wgmma.mma_async.sync.aligned.m64n64k16.f32.bf16.bf16 {"
      "%0, %1, %2, %3, %4, %5, %6, %7, %8, %9, %10, %11, %12, %13, %14, %15, "
      "%16, %17, %18, %19, %20, %21, %22, %23, %24, %25, %26, %27, %28, %29, %30, %31"
      "}, {%32, %33, %34, %35}, db, p, 1, 1, 1;\n}\n"
      : "+f"(d[0]), "+f"(d[1]), "+f"(d[2]), "+f"(d[3]), "+f"(d[4]), "+f"(d[5]), "+f"(d[6]), "+f"(d[7]),
        "+f"(d[8]), "+f"(d[9]), "+f"(d[10]), "+f"(d[11]), "+f"(d[12]), "+f"(d[13]), "+f"(d[14]), "+f"(d[15]),
        "+f"(d[16]), "+f"(d[17]), "+f"(d[18]), "+f"(d[19]), "+f"(d[20]), "+f"(d[21]), "+f"(d[22]), "+f"(d[23]),
        "+f"(d[24]), "+f"(d[25]), "+f"(d[26]), "+f"(d[27]), "+f"(d[28]), "+f"(d[29]), "+f"(d[30]), "+f"(d[31])
      : "r"(a[0]), "r"(a[1]), "r"(a[2]), "r"(a[3]), "r"(db), "n"(HB), "n"(1));
  }
  template <uint32_t HB>
  static __device__ __forceinline__ void set(float* d, const uint32_t* a, uint32_t db) {
    asm volatile("{\n.reg .pred p;\n.reg .b64 db;\nsetp.ne.b32 p, %38, 0;\n"
      "mov.b64 db, {%36, %37};\n"
      "wgmma.mma_async.sync.aligned.m64n64k16.f32.bf16.bf16 {"
      "%0, %1, %2, %3, %4, %5, %6, %7, %8, %9, %10, %11, %12, %13, %14, %15, "
      "%16, %17, %18, %19, %20, %21, %22, %23, %24, %25, %26, %27, %28, %29, %30, %31"
      "}, {%32, %33, %34, %35}, db, p, 1, 1, 1;\n}\n"
      : "=f"(d[0]), "=f"(d[1]), "=f"(d[2]), "=f"(d[3]), "=f"(d[4]), "=f"(d[5]), "=f"(d[6]), "=f"(d[7]),
        "=f"(d[8]), "=f"(d[9]), "=f"(d[10]), "=f"(d[11]), "=f"(d[12]), "=f"(d[13]), "=f"(d[14]), "=f"(d[15]),
        "=f"(d[16]), "=f"(d[17]), "=f"(d[18]), "=f"(d[19]), "=f"(d[20]), "=f"(d[21]), "=f"(d[22]), "=f"(d[23]),
        "=f"(d[24]), "=f"(d[25]), "=f"(d[26]), "=f"(d[27]), "=f"(d[28]), "=f"(d[29]), "=f"(d[30]), "=f"(d[31])
      : "r"(a[0]), "r"(a[1]), "r"(a[2]), "r"(a[3]), "r"(db), "n"(HB), "n"(0));
  }
};
template <> struct WgSST<48> {
  template <uint32_t HA, uint32_t HB>
  static __device__ __forceinline__ void mma(float* d, uint32_t da, uint32_t db, int sc) {
    asm volatile("{\n.reg .pred p;\n.reg .b64 da, db;\nsetp.ne.b32 p, %28, 0;\n"
      "mov.b64 da, {%24, %25};\nmov.b64 db, {%26, %27};\n"
      "wgmma.mma_async.sync.aligned.m64n48k16.f32.bf16.bf16 {"
      "%0, %1, %2, %3, %4, %5, %6, %7, %8, %9, %10, %11, %12, %13, %14, %15, "
      "%16, %17, %18, %19, %20, %21, %22, %23"
      "}, da, db, p, 1, 1, 0, 1;\n}\n"
      : "+f"(d[0]), "+f"(d[1]), "+f"(d[2]), "+f"(d[3]), "+f"(d[4]), "+f"(d[5]), "+f"(d[6]), "+f"(d[7]),
        "+f"(d[8]), "+f"(d[9]), "+f"(d[10]), "+f"(d[11]), "+f"(d[12]), "+f"(d[13]), "+f"(d[14]), "+f"(d[15]),
        "+f"(d[16]), "+f"(d[17]), "+f"(d[18]), "+f"(d[19]), "+f"(d[20]), "+f"(d[21]), "+f"(d[22]), "+f"(d[23])
      : "r"(da), "n"(HA), "r"(db), "n"(HB), "r"(sc));
  }
};
template <> struct WgSST<80> {
  template <uint32_t HA, uint32_t HB>
  static __device__ __forceinline__ void mma(float* d, uint32_t da, uint32_t db, int sc) {
    asm volatile("{\n.reg .pred p;\n.reg .b64 da, db;\nsetp.ne.b32 p, %44, 0;\n"
      "mov.b64 da, {%40, %41};\nmov.b64 db, {%42, %43};\n"
      "wgmma.mma_async.sync.aligned.m64n80k16.f32.bf16.bf16 {"
      "%0, %1, %2, %3, %4, %5, %6, %7, %8, %9, %10, %11, %12, %13, %14, %15, "
      "%16, %17, %18, %19, %20, %21, %22, %23, %24, %25, %26, %27, %28, %29, %30, %31, "
      "%32, %33, %34, %35, %36, %37, %38, %39"
      "}, da, db, p, 1, 1, 0, 1;\n}\n"
      : "+f"(d[0]), "+f"(d[1]), "+f"(d[2]), "+f"(d[3]), "+f"(d[4]), "+f"(d[5]), "+f"(d[6]), "+f"(d[7]),
        "+f"(d[8]), "+f"(d[9]), "+f"(d[10]), "+f"(d[11]), "+f"(d[12]), "+f"(d[13]), "+f"(d[14]), "+f"(d[15]),
        "+f"(d[16]), "+f"(d[17]), "+f"(d[18]), "+f"(d[19]), "+f"(d[20]), "+f"(d[21]), "+f"(d[22]), "+f"(d[23]),
        "+f"(d[24]), "+f"(d[25]), "+f"(d[26]), "+f"(d[27]), "+f"(d[28]), "+f"(d[29]), "+f"(d[30]), "+f"(d[31]),
        "+f"(d[32]), "+f"(d[33]), "+f"(d[34]), "+f"(d[35]), "+f"(d[36]), "+f"(d[37]), "+f"(d[38]), "+f"(d[39])
      : "r"(da), "n"(HA), "r"(db), "n"(HB), "r"(sc));
  }
};
template <> struct WgSST<192> {
  template <uint32_t HA, uint32_t HB>
  static __device__ __forceinline__ void mma(float* d, uint32_t da, uint32_t db, int sc) {
    asm volatile("{\n.reg .pred p;\n.reg .b64 da, db;\nsetp.ne.b32 p, %100, 0;\n"
      "mov.b64 da, {%96, %97};\nmov.b64 db, {%98, %99};\n"
      "wgmma.mma_async.sync.aligned.m64n192k16.f32.bf16.bf16 {"
      "%0, %1, %2, %3, %4, %5, %6, %7, %8, %9, %10, %11, %12, %13, %14, %15, "
      "%16, %17, %18, %19, %20, %21, %22, %23, %24, %25, %26, %27, %28, %29, %30, %31, "
      "%32, %33, %34, %35, %36, %37, %38, %39, %40, %41, %42, %43, %44, %45, %46, %47, "
      "%48, %49, %50, %51, %52, %53, %54, %55, %56, %57, %58, %59, %60, %61, %62, %63, "
      "%64, %65, %66, %67, %68, %69, %70, %71, %72, %73, %74, %75, %76, %77, %78, %79, "
      "%80, %81, %82, %83, %84, %85, %86, %87, %88, %89, %90, %91, %92, %93, %94, %95"
      "}, da, db, p, 1, 1, 0, 1;\n}\n"
      : "+f"(d[0]), "+f"(d[1]), "+f"(d[2]), "+f"(d[3]), "+f"(d[4]), "+f"(d[5]), "+f"(d[6]), "+f"(d[7]),
        "+f"(d[8]), "+f"(d[9]), "+f"(d[10]), "+f"(d[11]), "+f"(d[12]), "+f"(d[13]), "+f"(d[14]), "+f"(d[15]),
        "+f"(d[16]), "+f"(d[17]), "+f"(d[18]), "+f"(d[19]), "+f"(d[20]), "+f"(d[21]), "+f"(d[22]), "+f"(d[23]),
        "+f"(d[24]), "+f"(d[25]), "+f"(d[26]), "+f"(d[27]), "+f"(d[28]), "+f"(d[29]), "+f"(d[30]), "+f"(d[31]),
        "+f"(d[32]), "+f"(d[33]), "+f"(d[34]), "+f"(d[35]), "+f"(d[36]), "+f"(d[37]), "+f"(d[38]), "+f"(d[39]),
        "+f"(d[40]), "+f"(d[41]), "+f"(d[42]), "+f"(d[43]), "+f"(d[44]), "+f"(d[45]), "+f"(d[46]), "+f"(d[47]),
        "+f"(d[48]), "+f"(d[49]), "+f"(d[50]), "+f"(d[51]), "+f"(d[52]), "+f"(d[53]), "+f"(d[54]), "+f"(d[55]),
        "+f"(d[56]), "+f"(d[57]), "+f"(d[58]), "+f"(d[59]), "+f"(d[60]), "+f"(d[61]), "+f"(d[62]), "+f"(d[63]),
        "+f"(d[64]), "+f"(d[65]), "+f"(d[66]), "+f"(d[67]), "+f"(d[68]), "+f"(d[69]), "+f"(d[70]), "+f"(d[71]),
        "+f"(d[72]), "+f"(d[73]), "+f"(d[74]), "+f"(d[75]), "+f"(d[76]), "+f"(d[77]), "+f"(d[78]), "+f"(d[79]),
        "+f"(d[80]), "+f"(d[81]), "+f"(d[82]), "+f"(d[83]), "+f"(d[84]), "+f"(d[85]), "+f"(d[86]), "+f"(d[87]),
        "+f"(d[88]), "+f"(d[89]), "+f"(d[90]), "+f"(d[91]), "+f"(d[92]), "+f"(d[93]), "+f"(d[94]), "+f"(d[95])
      : "r"(da), "n"(HA), "r"(db), "n"(HB), "r"(sc));
  }
};

struct FftConst {
  uint32_t f[2][4], fi[4][4];
  uint32_t ta[2][2], tb[2][2];
};
__device__ __forceinline__ void cis(int m, float scale, float& c, float& s) {
  const float a = (float)m * (-6.283185307179586f * scale);
  c = __cosf(a);
  s = __sinf(a);
}
__device__ __forceinline__ void fft_tables(uint32_t (&v)[12], int tw) {
  const int row = tw >> 2, ch = tw & 3;
#pragma unroll
  for (int i = 0; i < 4; i++) {
    float c[2], s[2], x[2];
#pragma unroll
    for (int e = 0; e < 2; e++) {
      cis((((32 * (8 * ch + 2 * i + e) + 15) * (4 * row - 63) + 2048) & 4095) - 2048, 1.f / 4096, c[e], s[e]);
      float gc, gs;
      cis((((row & 15) * (8 * (ch & 1) + 2 * i + e) + 8) & 15) - 8, 1.f / 16, gc, gs);
      x[e] = (row >> 4) == (ch >> 1) ? gc : (ch >> 1) ? gs : -gs;
    }
    v[i] = pack2(c[0] * 0.125f, c[1] * 0.125f);
    v[4 + i] = pack2(s[0] * 0.125f, s[1] * 0.125f);
    v[8 + i] = pack2(x[0], x[1]);
  }
#pragma unroll
  for (int i = 0; i < 12; i++) asm volatile("" : "+r"(v[i]));
}
__device__ __forceinline__ void fft_tables_store(const uint32_t (&v)[12], uint32_t sb, int tw) {
  const int row = tw >> 2;
  const uint32_t x = ((tw ^ (row >> 1)) & 3) << 4, a = sb + OFF_FT + (16 * (row >> 3) + (row & 7)) * 64 + x;
  sts128(a, v[0], v[1], v[2], v[3]);
  sts128(a + 512, v[4], v[5], v[6], v[7]);
  sts128(sb + OFF_GT + row * 64 + x, v[8], v[9], v[10], v[11]);
}
__device__ __forceinline__ void fft_twiddles(uint32_t (&v)[2], int tw) {
  float a[2], s[2];
#pragma unroll
  for (int i = 0; i < 2; i++) {
    float c;
    cis((2 * (2 * (tw & 3) + i) - 15) * (4 * (tw >> 2) - 63), 1.f / 4096, c, s[i]);
    a[i] = __fdividef(-s[i], 1.f + c);
  }
  v[0] = pack2(a[0], a[1]);
  v[1] = pack2(s[0], s[1]);
  asm volatile("" : "+r"(v[0]), "+r"(v[1]));
}
__device__ __forceinline__ void fft_matrices(FftConst& k, uint32_t sb, int w, int lane) {
  const uint32_t x = (lane >> 1) & 3;
  const uint2 t0 = lds64(sb + OFF_TT + 256 * w + 8 * lane), t1 = lds64(sb + OFF_TT + 256 * w + 8 * (lane ^ 3));
  k.ta[0][0] = t0.x;
  k.tb[0][0] = t0.y;
  k.ta[1][1] = __byte_perm(t1.x, 0, 0x1032);
  k.tb[1][1] = __byte_perm(t1.y, 0, 0x1032);
#pragma unroll
  for (int j = 0; j < 2; j++) {
    k.ta[1 - j][j] = k.ta[j][j] ^ 0x80008000u;
    k.tb[1 - j][j] = k.tb[j][j] ^ 0x80008000u;
    asm volatile("" : "+r"(k.ta[0][j]), "+r"(k.tb[0][j]), "+r"(k.ta[1][j]), "+r"(k.tb[1][j]));
  }
#pragma unroll
  for (int i = 0; i < 2; i++) {
    ldsm4(k.f[i], sb + OFF_FT + (16 * w + (lane & 15)) * 64 + (((2 * i + (lane >> 4)) ^ x) << 4));
    ldsm4t(k.fi[i], sb + OFF_FT + (32 * i + lane) * 64 + ((w ^ x) << 4));
#pragma unroll
    for (int j = 0; j < 4; j++) {
      k.fi[2 + i][j] = (j & 1) ? k.fi[i][j - 1] ^ 0x80008000u : k.fi[i][j + 1];
      asm volatile("" : "+r"(k.fi[2 + i][j]));
    }
  }
}
__device__ __forceinline__ void rot(uint32_t& x, uint32_t& y, uint32_t a, uint32_t b) {
  x = bfma(a, y, x);
  y = bfma(b, x, y);
  x = bfma(a, y, x);
}
__device__ __forceinline__ void twiddle_fwd(uint32_t (&a)[4][4], float* d, const FftConst& k) {
#pragma unroll
  for (int q = 0; q < 4; q++)
#pragma unroll
    for (int j = 0; j < 2; j++) {
      const float* x = d + 8 * q + 4 * j;
      uint32_t re = pack2(x[0], x[1]), im = pack2(x[2], x[3]);
      rot(re, im, k.ta[0][j], k.tb[0][j]);
      a[q & 2][2 * j + (q & 1)] = re;
      a[(q & 2) + 1][2 * j + (q & 1)] = im;
    }
}
__device__ __forceinline__ void g_step(float* d, const uint32_t (&a)[4][4], uint32_t dre, uint32_t dim) {
  WgRS<32>::set<HI_SW64>(d, a[0], dre);
  WgRS<32>::set<HI_SW64>(d + 16, a[2], dre);
  WgRS<32>::mma<HI_SW64>(d, a[1], dim);
  WgRS<32>::mma<HI_SW64>(d + 16, a[3], dim);
  wg_commit();
}

__device__ __forceinline__ void products(uint32_t (&a)[4][4], const float* H, const float* U, int p) {
#pragma unroll
  for (int j = 0; j < 2; j++)
#pragma unroll
    for (int m = 2 * p; m < 2 * p + 2; m++) {
      float pr[2], pi[2];
#pragma unroll
      for (int x = 0; x < 2; x++)
#pragma unroll
        for (int q = 0; q <= m; q++) {
          const int ih = 16 * (q >> 1) + 2 * (q & 1) + 4 * j + x, iu = 16 * ((m - q) >> 1) + 2 * ((m - q) & 1) + 4 * j + x;
          pr[x] = q ? fmaf(H[ih], U[iu], pr[x]) : H[ih] * U[iu];
          pi[x] = q ? fmaf(H[ih], U[iu + 8], pi[x]) : H[ih] * U[iu + 8];
          pr[x] = fmaf(-H[ih + 8], U[iu + 8], pr[x]);
          pi[x] = fmaf(H[ih + 8], U[iu], pi[x]);
        }
      a[m & 2][2 * j + (m & 1)] = pack2(pr[0], pr[1]);
      a[(m & 2) + 1][2 * j + (m & 1)] = pack2(pi[0], pi[1]);
    }
}

__device__ __forceinline__ void f_step(float* d, const FftConst& k, uint32_t db) {
  WgRS<64>::set<HI_SW32>(d, k.f[0], db);
  WgRS<64>::mma<HI_SW32>(d, k.f[1], db + 32);
  wg_commit();
}
__device__ __forceinline__ void last_step(float* d, const FftConst& k, uint32_t dz) {
  wg_fence();
  WgRS<64>::set<HI_SW128>(d, k.fi[0], dz);
#pragma unroll
  for (int ks = 1; ks < 4; ks++) WgRS<64>::mma<HI_SW128>(d, k.fi[ks], dz + 128 * ks);
  wg_commit();
}
__device__ __forceinline__ void conv_channel(const FftConst& k, uint32_t (&a)[4][4], uint32_t sb, int c, int cn, int wg, int w, int lane) {
  const uint32_t cb = sb + off_ch(c), bars = sb + OFF_BAR;
  const uint32_t du = desc_lo(cb, 1024), dg = desc_lo(sb + OFF_GT, 16), dz = desc_lo(cb + U_BYTES, 16);
  float U[32], H[32];
  uint32_t e[4][4];
  const float dv = __uint_as_float(lds32(sb + OFF_D + 4 * c));
  if (ATT_GATE) mbar_wait(bars + 8 * (ATT_GATE == 1 ? B_ATTN : B_ATT2), 0);
  mbar_wait(bars + 8 * (B_U + (c < 3 ? c : 3)), 0);
  TSM(w == 0 && c < 3, 7 + wg);
  wg_fence();
  f_step(U, k, du);
  g_step(H, a, dg, dg + 64);
  wg_wait<1>();
  pin<32>(U);
  twiddle_fwd(e, U, k);
  wg_fence();
  g_step(U, e, dg, dg + 64);
  wg_wait<0>();
  pin<32>(U);
  pin<32>(H);
#pragma unroll
  for (int j = 0; j < 4; j++) H[4 * (j >> 1) + (j & 1)] += dv;
  float V[32];
#pragma unroll
  for (int p = 0; p < 2; p++) {
    products(a, H, U, p);
    wg_fence();
    WgRS<32>::set<HI_SW64>(V + 16 * p, a[2 * p], dg + 64);
    WgRS<32>::mma<HI_SW64>(V + 16 * p, a[2 * p + 1], dg);
    wg_commit();
  }
  const uint32_t za = cb + U_BYTES + (8 * w + (lane & 7)) * 128 + (((lane >> 3) ^ (lane & 7)) << 4);
  const uint32_t ya = cb + (lane >> 4) * 1024 + (8 * w + (lane & 7)) * 32 + ((((lane >> 3) ^ (lane >> 2)) & 1) << 4);
  wg_sync(1 + wg);
#pragma unroll
  for (int p = 0; p < 2; p++) {
    if (p == 0) wg_wait<1>();
    else wg_wait<0>();
    pin<16>(V + 16 * p);
#pragma unroll
    for (int i = 0; i < 4; i++) {
      const int j = i & 1;
      const float* x = V + 16 * p + 4 * j + (i & 2);
      e[p][i] = pack2(x[8], x[9]);
      e[2 + p][i] = pack2(x[0], x[1]);
      rot(e[p][i], e[2 + p][i], k.ta[1][j], k.tb[1][j]);
    }
    stsm4(za ^ (64 * p), e[p]);
    stsm4((za ^ (64 * p)) + 4096, e[2 + p]);
  }
  if (cn >= 0) {
    wg_fence();
    f_step(U, k, desc_lo(sb + off_ch(cn) + U_BYTES, 1024));
    fence_async_smem();
    wg_sync(1 + wg);
    last_step(H, k, dz);
    wg_wait<1>();
    pin<32>(U);
    twiddle_fwd(a, U, k);
    wg_wait<0>();
  } else {
    fence_async_smem();
    wg_sync(1 + wg);
    last_step(H, k, dz);
    wg_wait<0>();
  }
  pin<32>(H);
  if (WO_GATE == 4 && lane == 0) mbar_arrive(bars + 8 * B_CVD);
  TSIF(w == 0, 88 + c);
#pragma unroll
  for (int j = 0; j < 8; j++)
    e[j >> 2][j & 3] = j < 2 ? pack2(H[4 * j], H[4 * j + 1]) : pack2(H[4 * j] + H[4 * j - 6], H[4 * j + 1] + H[4 * j - 5]);
  stsm4(ya, e[0]);
  stsm4(ya + 2048, e[1]);
  fence_async_smem();
  __syncwarp();
}

__device__ __forceinline__ void prep_slab(uint4* res, const uint2* sw, uint32_t sb, int slab, int w, int lane) {
  const int t = lane & 3, tp = (lane & 7) >> 1, pos = 8 * tp + 2 * (((lane >> 3) + tp) & 3) + (lane & 1);
  const uint32_t base = sb + OFF_KVS + slab * KVS_BYTES + pos * 128;
  uint32_t kk[2][4][4], vv[2][4];
  mbar_wait(sb + OFF_BAR + 8 * (B_KV + slab), 0);
#pragma unroll
  for (int h = 0; h < 2; h++) {
#pragma unroll
    for (int j = 0; j < 4; j++) {
      const uint32_t a = base + 128 * j;
      ldsm4t(kk[h][j], a + (((w + 4 * h) ^ ((a >> 7) & 7)) << 4));
    }
    const uint32_t a = base + KVS_V;
    ldsm4t(vv[h], a + (((w + 4 * h) ^ ((a >> 7) & 7)) << 4));
  }
#pragma unroll
  for (int h = 0; h < 2; h++) {
    uint32_t (&k)[4][4] = kk[h];
    uint32_t (&v)[4] = vv[h];
    const uint32_t w0 = __byte_perm(sw[h].x, 0, 0x1010), w1 = __byte_perm(sw[h].x, 0, 0x3232);
    const uint32_t w2 = __byte_perm(sw[h].y, 0, 0x1010), w3 = __byte_perm(sw[h].y, 0, 0x3232);
#pragma unroll
    for (int m = 0; m < 4; m++)
      v[m] = bmul(badd(badd(badd(bmul(k[0][m], w3), bmul(k[1][m], w2)), bmul(k[2][m], w1)), bmul(k[3][m], w0)), v[m]);
    uint32_t a[4];
#pragma unroll
    for (int m = 0; m < 4; m++) a[m] = (t & 1) ? v[(m + 3) & 3] : v[m];
    res[h] = (t & 2) ? make_uint4(a[2], a[3], a[0], a[1]) : make_uint4(a[0], a[1], a[2], a[3]);
  }
}

__device__ __forceinline__ void prep_gate(const Params& p, uint32_t sb, int b, int w, int lane) {
  uint2 gw[5], x[4][5];
#pragma unroll
  for (int j = 0; j < 5; j++) gw[j] = ldg64(reinterpret_cast<const uint2*>(p.gate_w) + lane + 32 * j);
#pragma unroll
  for (int i = 0; i < 4; i++)
#pragma unroll
    for (int j = 0; j < 5; j++)
      x[i][j] = ldg64(reinterpret_cast<const uint2*>(p.q) + (16 * b + 4 * w + i) * (DIM / 4) + lane + 32 * j);
  float s[4];
#pragma unroll
  for (int i = 0; i < 4; i++) {
    s[i] = 0.f;
#pragma unroll
    for (int j = 0; j < 5; j++) {
      const uint32_t m0 = bmul(x[i][j].x, gw[j].x), m1 = bmul(x[i][j].y, gw[j].y);
      s[i] += (bf_lo(m0) + bf_hi(m0)) + (bf_lo(m1) + bf_hi(m1));
    }
  }
  const bool h = lane & 16, q = lane & 8;
  const float a = (h ? s[2] : s[0]) + __shfl_xor_sync(0xffffffffu, h ? s[0] : s[2], 16);
  const float c = (h ? s[3] : s[1]) + __shfl_xor_sync(0xffffffffu, h ? s[1] : s[3], 16);
  float z = (q ? c : a) + __shfl_xor_sync(0xffffffffu, q ? a : c, 8);
#pragma unroll
  for (int o = 4; o > 0; o >>= 1) z += __shfl_xor_sync(0xffffffffu, z, o);
  z = bf_lo(pack2(z, 0.f));
  z = bf_lo(pack2(__fdividef(1.f, 1.f + __expf(-z)), 0.f));
  if (G_TMA) {
    mbar_wait(sb + OFF_BAR + 8 * B_S3, 0);
    if ((lane & 7) == 0) asm volatile("st.shared.f32 [%0], %1;" ::"r"(sb + OFF_GATE + 64 * (b & 7) + 16 * w + (lane >> 1)), "f"(z) : "memory");
    fence_async_smem();
  } else if ((lane & 7) == 0) {
    g_gate[16 * b + 4 * w + (lane >> 3)] = z;
  }
}

__device__ __forceinline__ uint32_t bmax(uint32_t a, uint32_t b) {
  uint32_t d;
  asm("max.bf16x2 %0, %1, %2;" : "=r"(d) : "r"(a), "r"(b));
  return d;
}
__device__ __forceinline__ void softmax_two(const float (&l)[2][2], uint32_t& p0, uint32_t& p1) {
  constexpr float kScale = 0.22360679774997896f, kLog2e = 1.4426950408889634f;
  const uint32_t r0 = pack2(l[0][0], l[1][0]), r1 = pack2(l[0][1], l[1][1]);
  const uint32_t x0 = pack2(bf_lo(r0) * kScale, bf_hi(r0) * kScale), x1 = pack2(bf_lo(r1) * kScale, bf_hi(r1) * kScale);
  uint32_t m = bmax(x0, x1);
  m = bmax(m, __shfl_xor_sync(0xffffffffu, m, 1));
  m = bmax(m, __shfl_xor_sync(0xffffffffu, m, 2));
  const float m0 = bf_lo(m) * kLog2e, m1 = bf_hi(m) * kLog2e;
  p0 = pack2(ex2(bf_lo(x0) * kLog2e - m0), ex2(bf_lo(x1) * kLog2e - m0));
  p1 = pack2(ex2(bf_hi(x0) * kLog2e - m1), ex2(bf_hi(x1) * kLog2e - m1));
}

__device__ __forceinline__ void halo_read(uint32_t (&kpv)[10], uint32_t (&vpv)[10], uint32_t (&tg)[7], const uint4* hp) {
#pragma unroll
  for (int j = 0; j < 7; j++) {
    uint32_t x0, x1, x2;
    asm volatile("ld.relaxed.gpu.global.v4.u32 {%0, %1, %2, %3}, [%4];"
                 : "=r"(x0), "=r"(x1), "=r"(x2), "=r"(tg[j]) : "l"(hp + 32 * j) : "memory");
    if (j < 4) kpv[3 * j] = x0; else vpv[3 * j - 10] = x0;
    if (j < 3) kpv[3 * j + 1] = x1; else vpv[3 * j - 9] = x1;
    if (j < 3) kpv[3 * j + 2] = x2; else if (j < 6) vpv[3 * j - 8] = x2;
  }
}

template <int ROT>
__device__ __forceinline__ void pack_qkv(const float* acc, uint32_t (&qlo)[10], uint32_t (&qhi)[10], uint32_t (&klo)[10],
                                         uint32_t (&khi)[10], uint32_t (&vlo)[10], uint32_t (&vhi)[10]) {
#pragma unroll
  for (int j = 0; j < 10; j++) {
    const int x = (j + ROT) % 10, tq = x < 8 ? x : 16 + x, tk = x < 8 ? 8 + x : 18 + x, tv = x < 8 ? 16 + x : 20 + x;
    khi[j] = pack2(acc[4 * tk + 2], acc[4 * tk + 3]);
    vhi[j] = movm(pack2(acc[4 * tv + 2], acc[4 * tv + 3]));
    qlo[j] = pack2(acc[4 * tq], acc[4 * tq + 1]);
    qhi[j] = pack2(acc[4 * tq + 2], acc[4 * tq + 3]);
    klo[j] = pack2(acc[4 * tk], acc[4 * tk + 1]);
    vlo[j] = pack2(acc[4 * tv], acc[4 * tv + 1]);
    asm volatile("" : "+r"(khi[j]), "+r"(qlo[j]), "+r"(qhi[j]), "+r"(klo[j]), "+r"(vlo[j]));
  }
}

template <int ROT> __device__ __forceinline__ void halo_send(const float* acc, uint4* ho, uint32_t tag) {
#pragma unroll
  for (int j = 0; j < 7; j++) {
    uint32_t x[3];
#pragma unroll
    for (int e = 0; e < 3; e++) {
      const int i = 3 * j + e, y = (i % 10 + ROT) % 10, tk = y < 8 ? 8 + y : 18 + y, tv = y < 8 ? 16 + y : 20 + y;
      x[e] = i < 10 ? pack2(acc[4 * tk + 2], acc[4 * tk + 3]) : i < 20 ? movm(pack2(acc[4 * tv + 2], acc[4 * tv + 3])) : 0u;
    }
    asm volatile("st.relaxed.gpu.global.v4.u32 [%0], {%1, %2, %3, %4};" ::"l"(ho + 32 * j), "r"(x[0]), "r"(x[1]), "r"(x[2]), "r"(tag) : "memory");
  }
}

__device__ __forceinline__ void attention(float* acc, uint32_t sb, int b, int par, int w, int lane, uint32_t tag, uint32_t zero) {
  const int g = lane >> 2, t = lane & 3;
  uint32_t klo[10], khi[10], vlo[10], vhi[10], qlo[10], qhi[10], kpv[10], vpv[10];
  if (HALO_FIRST && w == 3 && b < NCTA - 8) {
    uint4* ho = g_halo + (b * 2 + par) * 224 + lane;
    if (tail_first(b & 7)) halo_send<8>(acc, ho, tag);
    else halo_send<0>(acc, ho, tag);
    TSIF(par == 0, 76);
    pin<120>(acc);
  }
  if (tail_first(b & 7)) pack_qkv<8>(acc, qlo, qhi, klo, khi, vlo, vhi);
  else pack_qkv<0>(acc, qlo, qhi, klo, khi, vlo, vhi);
  const uint32_t xa = sb + OFF_KVX + (par * 3) * 2560 + lane * 16;
  if (w < 3) {
    sts128(xa + w * 2560, khi[0], khi[1], khi[2], khi[3]);
    sts128(xa + w * 2560 + 512, khi[4], khi[5], khi[6], khi[7]);
    sts128(xa + w * 2560 + 1024, khi[8], khi[9], vhi[0], vhi[1]);
    sts128(xa + w * 2560 + 1536, vhi[2], vhi[3], vhi[4], vhi[5]);
    sts128(xa + w * 2560 + 2048, vhi[6], vhi[7], vhi[8], vhi[9]);
  } else if (!HALO_FIRST && b < NCTA - 8) {
    uint4* ho = g_halo + (b * 2 + par) * 224 + lane;
#pragma unroll
    for (int j = 0; j < 7; j++) {
      const uint32_t x0 = j < 4 ? khi[3 * j] : vhi[3 * j - 10], x1 = j < 3 ? khi[3 * j + 1] : vhi[3 * j - 9];
      const uint32_t x2 = j < 3 ? khi[3 * j + 2] : j < 6 ? vhi[3 * j - 8] : 0u;
      asm volatile("st.relaxed.gpu.global.v4.u32 [%0], {%1, %2, %3, %4};" ::"l"(ho + 32 * j), "r"(x0), "r"(x1), "r"(x2), "r"(tag) : "memory");
    }
  }
  TSIF(par == 0 && w == 1, 64);
  TSIF(par == 0 && w == 3 && !HALO_FIRST, 76);
#pragma unroll
  for (int j = 0; j < 10; j++) vlo[j] = movm(vlo[j]);
  const bool far0 = 2 * t > g, far1 = 2 * t + 1 > g;
  const uint32_t mfar = (far0 ? 0x0000FFFFu : 0u) | (far1 ? 0xFFFF0000u : 0u);
  float slo[4][2], shi[4][2], lg[2][2];
  uint32_t phi[4], plo[4], qml[4], qmh[4];
#pragma unroll
  for (int h = 0; h < 4; h++) {
    const int f = h == 0 ? 0 : h == 1 ? 3 : h == 2 ? 5 : 8, hf = h < 2 ? 2 : 7;
    const bool mine = (h & 1) ? t >= 2 : t < 2;
    qml[h] = mine ? qlo[hf] : 0u;
    qmh[h] = mine ? qhi[hf] : 0u;
    float a[4] = {0.f, 0.f, 0.f, 0.f}, c[4] = {0.f, 0.f, 0.f, 0.f};
    mma16816(a, qlo[f], qhi[f], qlo[f + 1], qhi[f + 1], klo[f], klo[f + 1]);
    mma16816(c, qlo[f], qhi[f], qlo[f + 1], qhi[f + 1], khi[f], khi[f + 1]);
    mma1688(a, qml[h], qmh[h], klo[hf]);
    mma1688(c, qml[h], qmh[h], khi[hf]);
    slo[h][0] = a[0];
    slo[h][1] = a[1];
    shi[h][0] = lg[h & 1][0] = far0 ? a[2] : c[2];
    shi[h][1] = lg[h & 1][1] = far1 ? a[3] : c[3];
    if (!ATT_MERGE && (h & 1)) softmax_two(lg, phi[h - 1], phi[h]);
  }
  TSIF(par == 0 && w == 1, 65);
  if (ATT_GATE == 3 && lane == 0) mbar_arrive(sb + OFF_BAR + 8 * B_ATT2 + (phi[3] & zero));
  wg_sync(1 + par);
  TSIF(par == 0 && w == 1, 66);
  const bool nohist = (w == 0) && (b < 8);
  const uint4* hp = g_halo + ((b - 8) * 2 + par) * 224 + lane;
  uint32_t tg[7];
  if (w > 0) {
    const uint4 v0 = lds128(xa + (w - 1) * 2560), v1 = lds128(xa + (w - 1) * 2560 + 512), v2 = lds128(xa + (w - 1) * 2560 + 1024);
    const uint4 v3 = lds128(xa + (w - 1) * 2560 + 1536), v4 = lds128(xa + (w - 1) * 2560 + 2048);
    kpv[0] = v0.x; kpv[1] = v0.y; kpv[2] = v0.z; kpv[3] = v0.w; kpv[4] = v1.x; kpv[5] = v1.y; kpv[6] = v1.z; kpv[7] = v1.w;
    kpv[8] = v2.x; kpv[9] = v2.y; vpv[0] = v2.z; vpv[1] = v2.w; vpv[2] = v3.x; vpv[3] = v3.y; vpv[4] = v3.z; vpv[5] = v3.w;
    vpv[6] = v4.x; vpv[7] = v4.y; vpv[8] = v4.z; vpv[9] = v4.w;
  } else if (nohist) {
#pragma unroll
    for (int j = 0; j < 10; j++) kpv[j] = vpv[j] = 0u;
  } else {
    TSIF(par == 0, 77);
    halo_read(kpv, vpv, tg, hp);
  }
  if (w == 0 && !nohist) {
    int spins = 0;
    while (true) {
      bool ok = true;
#pragma unroll
      for (int j = 0; j < 7; j++) ok = ok && tg[j] == tag;
      if (__all_sync(0xffffffffu, ok) || ++spins > SPIN_LIMIT) break;
      halo_read(kpv, vpv, tg, hp);
    }
    TSIF(par == 0, 79);
  }
#pragma unroll
  for (int h = 0; h < 4; h++) {
    const int f = h == 0 ? 0 : h == 1 ? 3 : h == 2 ? 5 : 8, hf = h < 2 ? 2 : 7;
    float a[4] = {0.f, 0.f, 0.f, 0.f};
    mma16816(a, qlo[f], qhi[f], qlo[f + 1], qhi[f + 1], kpv[f], kpv[f + 1]);
    mma1688(a, qml[h], qmh[h], kpv[hf]);
    const float ninf = __int_as_float(0xff800000);
    lg[h & 1][0] = far0 ? (nohist ? ninf : a[0]) : slo[h][0];
    lg[h & 1][1] = far1 ? (nohist ? ninf : a[1]) : slo[h][1];
    if (h & 1) {
      softmax_two(lg, plo[h - 1], plo[h]);
      if (ATT_MERGE) {
        const float lh[2][2] = {{shi[h - 1][0], shi[h - 1][1]}, {shi[h][0], shi[h][1]}};
        softmax_two(lh, phi[h - 1], phi[h]);
      }
    }
  }
  TSIF(par == 0 && w <= 1, 67 + w);
  if (ATT_GATE == 2 && lane == 0) mbar_arrive(sb + OFF_BAR + 8 * B_ATT2 + (plo[3] & zero));
  uint32_t ov[20];
#pragma unroll
  for (int hp = 0; hp < 2; hp++) {
    const int hf = hp ? 7 : 2;
    float sh[4] = {0.f, 0.f, 0.f, 0.f}, i0 = 0.f, i1 = 0.f;
#pragma unroll
    for (int e = 0; e < 2; e++) {
      const int h = 2 * hp + e, f = h == 0 ? 0 : h == 1 ? 3 : h == 2 ? 5 : 8;
      const uint32_t a0 = plo[h] & mfar, a2 = plo[h] & ~mfar, a3 = phi[h] & mfar, c1 = phi[h] & ~mfar;
      float sum[4] = {0.f, 0.f, 0.f, 0.f};
      mma1688(sum, plo[h], phi[h], 0x3F803F80u);
      const float r0 = rcp(sum[0]), r1 = rcp(sum[2]);
#pragma unroll
      for (int j = f; j < f + 2; j++) {
        float o[4] = {0.f, 0.f, 0.f, 0.f};
        mma16816(o, a0, 0u, a2, a3, vpv[j], vlo[j]);
        mma1688(o, 0u, c1, vhi[j]);
        ov[2 * j] = pack2(o[0] * r0, o[1] * r0);
        ov[2 * j + 1] = pack2(o[2] * r1, o[3] * r1);
      }
      const bool mine = e ? g >= 4 : g < 4;
      mma16816(sh, a0, 0u, a2, a3, mine ? vpv[hf] : 0u, mine ? vlo[hf] : 0u);
      mma1688(sh, 0u, c1, mine ? vhi[hf] : 0u);
      if (e == 0 || t >= 2) {
        i0 = r0;
        i1 = r1;
      }
    }
    ov[2 * hf] = pack2(sh[0] * i0, sh[1] * i0);
    ov[2 * hf + 1] = pack2(sh[2] * i1, sh[3] * i1);
  }
  if (ATT_GATE == 4 && lane == 0) mbar_arrive(sb + OFF_BAR + 8 * B_ATT2 + (ov[19] & zero));
  TS(32 + 4 * par + w);
  mbar_wait(sb + OFF_BAR + 8 * B_P1, 0);
  const uint32_t oa = sb + OFF_OA + (lane >> 4) * 2048 + (32 * w + 2 * (lane & 15) + par) * 16;
#pragma unroll
  for (int j = 0; j < 5; j++) stsm4(oa + 4096 * j, ov + 4 * j);
  TSIF(par == 0 && w == 0, 120);
  fence_async_smem();
  TSIF(par == 0 && w == 0, 121);
  __syncwarp();
  if (lane == 0) mbar_arrive(sb + OFF_BAR + 8 * B_ATTN);
  TSM(w == 0 || w == 2, 122 + par + (w == 2 ? 3 : 0));
}

struct Maps {
  CUtensorMap x, wm, wt, k, v, y, wo, qm, qt, om, ot, u;
};

__device__ __forceinline__ void load_stage(uint32_t sb, int kb, int b, const Maps& m) {
  const uint32_t st = sb + (kb & 3) * STAGE_BYTES, bar = sb + OFF_BAR + 8 * (B_FULL1 + (kb & 3));
  const int r = b >> 3, hg = b & 7, slab = kb - KV_KB;
  const bool kv = slab >= 0 && slab < 5;
  const uint32_t kbar = sb + OFF_BAR + 8 * (B_KV + slab), dst = sb + OFF_KVS + slab * KVS_BYTES;
  mbar_expect_tx(bar, STAGE_BYTES);
  if (kv) mbar_expect_tx(kbar, KVS_BYTES);
  tma_3d(st, &m.x, 64 * kb, 64 * r, 0, bar);
  if (kv && KV_MIX) tma_3d(dst, &m.k, 0, 32 * (b >> 1) - 3, 2 * slab + (b & 1), kbar);
  tma_3d(st + ST_W, &m.wm, 80 * hg + (tail_first(hg) ? 16 : 0), 64 * kb, 0, bar);
  if (kv && KV_MIX) tma_3d(dst + KVS_V, &m.v, 0, 32 * (b >> 1), 2 * slab + (b & 1), kbar);
  tma_3d(st + ST_WT, &m.wt, 80 * hg + (tail_first(hg) ? 0 : 64), 64 * kb, 0, bar);
  if (kv && !KV_MIX) tma_3d(dst, &m.k, 0, 32 * (b >> 1) - 3, 2 * slab + (b & 1), kbar);
  if (kv && !KV_MIX) tma_3d(dst + KVS_V, &m.v, 0, 32 * (b >> 1), 2 * slab + (b & 1), kbar);
}

__global__ void __launch_bounds__(NTHR, 1) fused_kernel(const __grid_constant__ Maps m, const Params p) {
  extern __shared__ __align__(1024) uint8_t smem[];
  const uint32_t sb = (uint32_t)__cvta_generic_to_shared(smem);
  const uint32_t bars = sb + OFF_BAR;
  const int tid = threadIdx.x, lane = tid & 31;
  int b = blockIdx.x;
  if (BMAP == 1) b = (((b & 63) >> 3) * 2 + (b & 1)) * 8 + (((b < 64 ? 0x6521 : 0x7430) >> (4 * ((b >> 1) & 3))) & 7);
  if (BMAP == 2) b = ((b & 63) >> 2) * 8 + (((b < 64 ? 0x6521 : 0x7430) >> (4 * (b & 3))) & 7);
  if (BMAP == 3) b = (((b & 63) >> 3) * 2 + (b & 1)) * 8 + (((b < 64 ? 0x7430 : 0x6521) >> (4 * ((b >> 1) & 3))) & 7);
  if (BMAP == 4) b = (((b >> 4) * 2 + (b & 1)) * 8) + ((b >> 1) & 7);
  if (BMAP == 5) b = 127 - b;
  const int r = b >> 3, hg = b & 7;

  if (tid == T_ISSUE) {
    TSM(true, 0);
#pragma unroll
    for (int i = 0; i < 4; i++) mbar_init(bars + 8 * (B_FULL1 + i), 1);
#pragma unroll
    for (int i = 0; i < 3; i++) mbar_init(bars + 8 * (B_KV + i), 1);
    fence_async_smem();
#pragma unroll 1
    for (int kb = 0; kb <= PRE2; kb++) load_stage(sb, kb, b, m);
  } else if (tid >= T_PF && tid < T_PF + 12) {
    tm_prefetch(&m.x + (tid - T_PF));
  } else if (tid == T_INIT) {
#pragma unroll
    for (int i = 0; i < 4; i++) mbar_init(bars + 8 * (B_EMPTY1 + i), 8);
#pragma unroll
    for (int i = 0; i < 8; i++) mbar_init(bars + 8 * (B_FULL2 + i), 1);
#pragma unroll
    for (int i = 0; i < 4; i++) mbar_init(bars + 8 * (B_EMPTY2 + i), 8);
#pragma unroll
    for (int i = 0; i < 4; i++) mbar_init(bars + 8 * (B_U + i), 1);
    mbar_init(bars + 8 * B_HA, 4);
    mbar_init(bars + 8 * B_GATE, 4);
    mbar_init(bars + 8 * B_HB, 1);
    mbar_init(bars + 8 * B_KVD, 4);
    mbar_init(bars + 8 * B_QF, 1);
    mbar_init(bars + 8 * B_ATTN, 8);
    mbar_init(bars + 8 * B_ATT2, 8);
    mbar_init(bars + 8 * B_P1, 8);
    mbar_init(bars + 8 * B_C34, 1);
    mbar_init(bars + 8 * B_YRB, 1);
#pragma unroll
    for (int i = 0; i < 5; i++) mbar_init(bars + 8 * (B_YST + i), 4);
#pragma unroll
    for (int i = 0; i < 5; i++) mbar_init(bars + 8 * (B_US + i), U_TMA ? 4 : i == 2 ? 20 : 1);
    mbar_init(bars + 8 * B_YSIG, 1);
    mbar_init(bars + 8 * B_YFULL, 1);
    mbar_init(bars + 8 * B_EPOCH, 1);
    mbar_init(bars + 8 * B_PREP, 4);
    mbar_init(bars + 8 * B_USIG, 1);
    mbar_init(bars + 8 * B_WST, 1);
#pragma unroll
    for (int i = 3; i < 5; i++) mbar_init(bars + 8 * (B_KV + i), 1);
    mbar_init(bars + 8 * B_E3, 8);
    mbar_init(bars + 8 * B_LAST, 1);
    mbar_init(bars + 8 * B_OSIG, 1);
    mbar_init(bars + 8 * B_WOP, 1);
    fence_async_smem();
  }
  const int warp = __shfl_sync(0xffffffffu, tid >> 5, 0), wg = warp >> 2, w = warp & 3;
  __syncthreads();

  if (wg == 3) {
    asm volatile("setmaxnreg.dec.sync.aligned.u32 56;");
    if (w == 0) {
      if (lane == 0) {
#pragma unroll 1
        for (int kb = 1 + PRE2; kb < 10; kb++) {
          if (kb >= 4) mbar_wait(bars + 8 * (kb == 7 ? B_E3 : B_EMPTY1 + (kb & 3)), (kb >> 3) & 1);
          TSIF(kb >= 4, 44 + kb);
          load_stage(sb, kb, b, m);
          TSIF(kb == 3, 60);
          if (kb == TRIG_KB) mbar_arrive(bars + 8 * B_LAST);
        }
        mbar_wait(bars + 8 * B_WOP, 0);
        mbar_wait(bars + 8 * WL_TRIG, 0);
        mbar_wait(bars + 8 * B_EPOCH, 0);
        flag_wait(g_cnt + C_W + 32 * hg, (lds32(sb + OFF_EPOCH) + 1) * 16);
        TS(30);
#pragma unroll 1
        for (int j = 0; j < 8; j++) {
          if (j >= 6) mbar_wait(bars + 8 * (B_EMPTY2 + j - 6), 0);
          if (j == 4) mbar_wait(bars + 8 * B_ATTN, 0);
          TSIF(j >= 6, 100 + j);
          if (RF_GATE && j == 6) mbar_wait(bars + 8 * B_YSIG, 0);
          mbar_expect_tx(bars + 8 * (B_FULL2 + j), j == 0 ? WO_BYTES : j == 5 ? O_BYTES + WO_BYTES + 512 : O_BYTES + WO_BYTES);
          bulk_load(sb + off_w(j), g_WO + (hg * 8 + step_src(hg, j)) * 800, WO_BYTES, bars + 8 * (B_FULL2 + j));
        }
        mbar_wait(bars + 8 * (B_EMPTY2 + Q_SLOT), 0);
        mbar_expect_tx(bars + 8 * B_QF, O_BYTES);
        tma_2d(sb + OFF_QS, &m.qm, 80 * hg, 128 * r, bars + 8 * B_QF);
        if (!QBOX) tma_2d(sb + OFF_QT, &m.qt, 80 * hg + 64, 128 * r, bars + 8 * B_QF);
      }
    } else if (w == 1) {
      unsigned epoch = 0;
      if (lane == 0) {
        epoch = atomicAdd(g_cnt + C_LAUNCH, 1u) / NCTA;
        asm volatile("st.shared.u32 [%0], %1;" ::"r"(sb + OFF_EPOCH), "r"(epoch) : "memory");
        mbar_arrive(bars + 8 * B_EPOCH);
        mbar_wait(bars + 8 * B_KVD, 0);
        mbar_expect_tx(bars + 8 * B_HB, 5 * 4096);
#pragma unroll 1
        for (int c = 0; c < 5; c++) {
          if (c == 3) mbar_wait(bars + 8 * B_S3, 0);
          bulk_load(sb + off_ch(c) + U_BYTES, p.ssm_k + (5 * b + c) * SEQ, 4096, bars + 8 * B_HB);
        }
#pragma unroll
        for (int c = 0; c < 4; c++) mbar_expect_tx(bars + 8 * (B_U + c), c < 3 ? U_BYTES : 2 * U_BYTES);
        const uint4* usrc = g_U + 5 * b * U_PITCH;
        mbar_wait(bars + 8 * B_USIG, 0);
        flag_wait(g_cnt + C_PREP + 32 * (b & 15), (epoch + 1) * NCTA);
        TS(23);
#pragma unroll
        for (int c = 0; c < 5; c++) {
          if (c == 3 && U_TRIM) mbar_wait(bars + 8 * (B_U + 2), 0);
          bulk_load(sb + off_ch(c), usrc + c * U_PITCH, U_BYTES, bars + 8 * (B_U + (c < 3 ? c : 3)));
          TSIF(c == 0 || c == 4, 116 + (c >> 2));
        }
      }
      epoch = __shfl_sync(0xffffffffu, epoch, 0);
      if (lane < 8) {
        const int src = (b & ~7) | step_src(hg, lane);
        mbar_wait(bars + 8 * OP_TRIG, 0);
        TS(20);
        bool seen = false;
#pragma unroll 1
        for (int spins = 0; spins < SPIN_LIMIT; spins++) {
          const bool now = !seen && (int)(flag_read(g_cnt + C_O + 32 * src) - (epoch + 1)) >= 0;
          if (now && lane >= 1 && lane < 4) bulk_load(sb + off_o(lane), g_O + src * 1280, O_BYTES, bars + 8 * (B_FULL2 + lane));
          seen = seen || now;
          if (__all_sync(0xff, seen)) break;
        }
        TS(21);
        if (lane == 5) bulk_load(sb + OFF_GATE, g_gate + 128 * r, 512, bars + 8 * (B_FULL2 + 5));
#pragma unroll 1
        for (int j = 4; j < 8; j++) {
          if (lane == j) {
            mbar_wait(bars + 8 * (j < 6 ? B_C34 : B_EMPTY2 + j - 6), 0);
            if (RF_GATE && j == 6) mbar_wait(bars + 8 * B_YSIG, 0);
            bulk_load(sb + off_o(j), g_O + src * 1280, O_BYTES, bars + 8 * (B_FULL2 + j));
          }
          __syncwarp(0xff);
        }
        TS(22);
      }
    } else if (w == 2) {
      mbar_wait(bars + 8 * B_PREP, 0);
      flag_signal(g_cnt + C_PREP, 16, lane);
      TS(25);
      if (lane == 0) {
        mbar_arrive(bars + 8 * B_USIG);
        mbar_expect_tx(bars + 8 * B_ORB, O_BYTES + 64);
        mbar_wait(bars + 8 * B_GATE, 0);
        bulk_store(g_gate + 16 * b, sb + OFF_GATE + 64 * hg, 64);
        bulk_wait_read<0>();
        bulk_load(sb + OFF_GATE + 64 * hg, g_gate + 16 * b, 64, bars + 8 * B_ORB);
        mbar_wait(bars + 8 * B_ATTN, 0);
        constexpr uint32_t PB = O_BYTES / O_SPLIT;
#pragma unroll
        for (int i = 0; i < O_SPLIT; i++) bulk_store(g_O + b * 1280 + i * (PB / 16), sb + OFF_OA + i * PB, PB);
#pragma unroll
        for (int i = 0; i < O_SPLIT; i++) {
          if (O_SPLIT - 1 - i == 4) bulk_wait_read<4>();
          if (O_SPLIT - 1 - i == 3) bulk_wait_read<3>();
          if (O_SPLIT - 1 - i == 2) bulk_wait_read<2>();
          if (O_SPLIT - 1 - i == 1) bulk_wait_read<1>();
          if (O_SPLIT - 1 - i == 0) bulk_wait_read<0>();
          bulk_load(sb + OFF_OA + i * PB, g_O + b * 1280 + i * (PB / 16), PB, bars + 8 * B_ORB);
        }
        TS(74);
        mbar_wait(bars + 8 * B_ORB, 0);
        flag_bump(g_cnt + C_O + 32 * b);
        TS(26);
        mbar_arrive(bars + 8 * B_OSIG);
      }
    } else {
      if (lane == 0) {
        uint4* dst = g_WO + (hg * 8 + (r >> 1)) * 800 + (r & 1) * 80;
        if (WPF) {
          mbar_wait(bars + 8 * WPF, 0);
          if (WPF_LIN)
            asm volatile("cp.async.bulk.prefetch.L2.global [%0], 6400;" ::"l"(p.wo + b * 3200) : "memory");
          else
            asm volatile("cp.async.bulk.prefetch.tensor.3d.L2.global [%0, {%1, %2, %3}];" ::"l"(&m.wo), "r"(0), "r"(40 * r), "r"(5 * hg) : "memory");
        }
        mbar_wait(bars + 8 * B_P1, 0);
        mbar_wait(bars + 8 * WB_TRIG, 0);
        mbar_expect_tx(bars + 8 * B_WST, WO_BYTES / 2);
        tma_3d(sb + OFF_WS, &m.wo, 0, 40 * r, 5 * hg, bars + 8 * B_WST);
        mbar_wait(bars + 8 * B_WST, 0);
        mbar_wait(bars + 8 * WO_TRIG, 0);
#pragma unroll 1
        for (int n = 0; n < 5; n++)
          asm volatile("cp.async.bulk.global.shared::cta.bulk_group [%0], [%1], 1280;" ::"l"(dst + 160 * n), "r"(sb + OFF_WS + 1280 * n) : "memory");
        if (W_RB) {
          asm volatile("cp.async.bulk.commit_group;\ncp.async.bulk.wait_group.read 0;" ::: "memory");
          mbar_expect_tx(bars + 8 * B_WST, WO_BYTES / 2);
#pragma unroll 1
          for (int n = 0; n < 5; n++) bulk_load(sb + OFF_WS + 1280 * n, dst + 160 * n, 1280, bars + 8 * B_WST);
          mbar_wait(bars + 8 * B_WST, 1);
        } else {
          asm volatile("cp.async.bulk.commit_group;\ncp.async.bulk.wait_group 0;\nfence.proxy.async.global;" ::: "memory");
          if (!(NOMB & 4)) asm volatile("fence.release.gpu;" ::: "memory");
        }
        flag_bump(g_cnt + C_W + 32 * hg);
        mbar_arrive(bars + 8 * B_WOP);
        TS(71);
        mbar_expect_tx(bars + 8 * B_C34, 3 * U_BYTES);
        mbar_expect_tx(bars + 8 * B_YRB, 2 * U_BYTES);
#pragma unroll 1
        for (int c = 0; c < 5; c++) {
          mbar_wait(bars + 8 * (B_YST + c), 0);
          asm volatile("cp.async.bulk.global.shared::cta.bulk_group [%0], [%1], 4096;\ncp.async.bulk.commit_group;\n"
                       "cp.async.bulk.wait_group.read 0;" ::"l"(g_Y + (5 * b + c) * Y_PITCH), "r"(sb + off_ch(c)) : "memory");
          bulk_load(sb + off_ch(c), g_Y + (5 * b + c) * Y_PITCH, U_BYTES, bars + 8 * (c < 3 ? B_C34 : B_YRB));
        }
        TS(75);
        mbar_wait(bars + 8 * B_C34, 0);
        mbar_wait(bars + 8 * B_YRB, 0);
        flag_bump(g_cnt + C_Y + 32 * (b >> 4));
        TS(27);
        mbar_arrive(bars + 8 * B_YSIG);
        mbar_expect_tx(bars + 8 * B_YFULL, 20480);
        flag_wait(g_cnt + C_Y + 32 * hg, (lds32(sb + OFF_EPOCH) + 1) * 16);
        TS(24);
        tma_2d(sb + OFF_YT, &m.y, 128 * r, 80 * hg, bars + 8 * B_YFULL);
        tma_2d(sb + OFF_YT + 10240, &m.y, 128 * r + 64, 80 * hg, bars + 8 * B_YFULL);
      }
    }
  } else {
    asm volatile("setmaxnreg.inc.sync.aligned.u32 152;");
    if (wg < 2) {
      float acc[120];
#pragma unroll
      for (int i = 0; i < 120; i++) acc[i] = 0.f;
      const uint32_t da = desc_lo(sb + wg * 8192, 16), db = desc_lo(sb + ST_W, 8192), dc = desc_lo(sb + ST_WT, 2048);
      if (PW1) pin<120>(acc);
      if (PW1 == 2) mbar_wait(bars + 8 * B_FULL1, 0);
#pragma unroll 1
      for (int kb = 0; kb < 10; kb++) {
        mbar_wait(bars + 8 * (B_FULL1 + (kb & 3)), (kb >> 2) & 1);
        const uint32_t so = (kb & 3) * (STAGE_BYTES >> 4);
        wg_fence();
#pragma unroll
        for (int k = 0; k < 4; k++) {
          WgSST<192>::mma<HI_SW128, HI_SW128>(acc, da + so + 2 * k, db + so + 128 * k, 1);
          WgSST<48>::mma<HI_SW128, HI_SW32>(acc + 96, da + so + 2 * k, dc + so + 32 * k, 1);
        }
        wg_commit();
        wg_wait<1>();
        if (kb > 0 && lane == 0) mbar_arrive(bars + 8 * (kb == 4 ? B_E3 : B_EMPTY1 + ((kb - 1) & 3)));
      }
      mbar_wait(bars + 8 * B_EPOCH, 0);
      const uint32_t tag = lds32(sb + OFF_EPOCH) + 1;
      mbar_wait(bars + 8 * B_S3, 0);
      wg_wait<0>();
      pin<120>(acc);
      if (lane == 0) mbar_arrive(bars + 8 * B_P1);
      TSM(w == 0, 3 + wg);
      attention(acc, sb, b, wg, w, lane, tag, p.zero);
    } else {
      const int tw = tid & 127, chl = 64 * (b & 1) + 8 * w + (lane >> 2);
      uint4* up = g_U + chl * U_PITCH + ((4 * (b >> 1) + (lane & 3)) ^ ((b >> 2) & 1));
      uint2 sw[10];
      uint32_t dv = 0;
      if (lane < 5) dv = __ldg(reinterpret_cast<const unsigned short*>(p.ssm_D) + 5 * b + lane);
#pragma unroll
      for (int i = 0; i < 10; i++) sw[i] = ldg64(reinterpret_cast<const uint2*>(p.shift_k) + chl + 128 * (i >> 1) + 32 * (i & 1));
      uint32_t tab[12];
      uint32_t tt[2];
      fft_tables(tab, tw);
      fft_twiddles(tt, tw);
      uint4 res[10];
#pragma unroll
      for (int i = 0; i < 10; i++) res[i] = make_uint4(0, 0, 0, 0);
#pragma unroll 1
      for (int slab = 0; slab < 5; slab++) {
#pragma unroll
        for (int i = 0; i < 8; i++) res[i] = res[i + 2];
        prep_slab(res + 8, sw, sb, slab, w, lane);
        TSIF(w == 0, 99 + 4 * slab);
#pragma unroll
        for (int i = 0; i < 8; i++) sw[i] = sw[i + 2];
      }
      TSIF(w == 0, 28);
      __syncwarp();
      if (lane == 0) mbar_arrive(bars + 8 * B_KVD + ((res[8].x ^ res[9].x) & p.zero));
      mbar_wait(bars + 8 * B_KVD, 0);
      fft_tables_store(tab, sb, tw);
      mbar_wait(bars + 8 * B_LAST, 0);
#pragma unroll
      for (int i = 0; i < 10; i++) up[(128 * (i >> 1) + 32 * (i & 1)) * U_PITCH] = res[i];
      __syncwarp();
      if (lane == 0) mbar_arrive(bars + 8 * B_PREP);
      TSIF(w == 0 && !U_TMA, 5);
      mbar_wait(bars + 8 * (G_AFTER ? B_USIG : B_LAST), 0);
      prep_gate(p, sb, b, w, lane);
      __syncwarp();
      if (lane == 0) mbar_arrive(bars + 8 * B_GATE);
      TSIF(w == 0, 72);
      mbar_wait(bars + 8 * B_HB, 0);
      TSIF(w == 0, 2);
      const uint32_t ha = sb + U_BYTES + ((tw >> 3) * 16 + 8 + (tw & 7)) * 16;
      uint4 hv[5];
#pragma unroll
      for (int c = 0; c < 5; c++) hv[c] = lds128(ha + off_ch(c));
      __syncwarp();
#pragma unroll
      for (int c = 0; c < 5; c++) sts128((ha ^ 16) + off_ch(c), hv[c].x, hv[c].y, hv[c].z, hv[c].w);
      asm volatile("st.shared.v2.u32 [%0], {%1, %2};" ::"r"(sb + OFF_TT + 8 * tw), "r"(tt[0]), "r"(tt[1]) : "memory");
      if (tw < 5) asm volatile("st.shared.f32 [%0], %1;" ::"r"(sb + OFF_D + 4 * tw), "f"(bf_lo(dv) * 0.125f) : "memory");
      fence_async_smem();
      __syncwarp();
      if (lane == 0) mbar_arrive(bars + 8 * B_HA);
      TSIF(w == 0, 6);
    }

    FftConst fc;
    TSM(w == 0 && wg == 0, 104);
    mbar_wait(bars + 8 * B_HA, 0);
    fft_matrices(fc, sb, w, lane);
    TSM(w == 0 && wg == 0, 105);
    TSM(w == 0 && wg == 2, 124);
    uint32_t tasks = wg == 0 ? TASK0 : wg == 1 ? TASK1 : TASK2, fa[4][4];
    {
      float X[32];
      wg_fence();
      f_step(X, fc, desc_lo(sb + off_ch((tasks & 7) - 1) + U_BYTES, 1024));
      wg_wait<0>();
      pin<32>(X);
      twiddle_fwd(fa, X, fc);
    }
#pragma unroll 1
    for (; tasks; tasks >>= 4) {
      const int c = (tasks & 7) - 1;
      conv_channel(fc, fa, sb, c, ((tasks >> 4) & 7) - 1, wg, w, lane);
      if (lane == 0) mbar_arrive(bars + 8 * (B_YST + c));
      TSM(w == 0, 10 + c);
    }

    if (wg != WO_SKIP) {
      const int wg = (warp >> 2) > WO_SKIP ? (warp >> 2) - 1 : warp >> 2;
      const int g = lane >> 2;
      float acc[40];
#pragma unroll
      for (int i = 0; i < 40; i++) acc[i] = 0.f;
      const uint32_t da = desc_lo(sb + wg * 1024, 2048), db = desc_lo(sb, 2560);
      mbar_wait(bars + 8 * (O_RB == 2 ? B_ORB : B_ATTN), 0);
      if (PW2) mbar_wait(bars + 8 * B_FULL2, 0);
      mbar_wait(bars + 8 * B_CVD, 0);
      TSM(w == 0, 15 + wg);
#pragma unroll 1
      for (int j = 0; j < 8; j++) {
        mbar_wait(bars + 8 * (B_FULL2 + j), 0);
        TSM(w == 0 && wg == 0, 44 + (j < 4 ? j : j + 6));
        const uint32_t oa = da + (off_o(j) >> 4), ob = db + (off_w(j) >> 4);
        wg_fence();
#pragma unroll
        for (int k = 0; k < 5; k++) WgSST<80>::mma<HI_NONE, HI_SW32>(acc, oa + 256 * k, ob + 32 * k, 1);
        wg_commit();
        wg_wait<1>();
        if (j >= 1 && j <= Q_SLOT + 1 && lane == 0) mbar_arrive(bars + 8 * (B_EMPTY2 + j - 1));
      }
      TSIF(w == 0 && wg == 0, 113);
      const int tr = 64 * wg + 16 * w + (lane & 15);
      const uint32_t fm = sb + OFF_QS + tr * 128, fx = (lane >> 4) ^ (tr & 7), fq = sb + OFF_QS + tr * 160 + (lane >> 4) * 16;
      const uint32_t ft = sb + OFF_QT + tr * 32 + (((lane >> 4) ^ (tr >> 2)) & 1) * 16;
      const float g0 = __uint_as_float(lds32(sb + OFF_GATE + (64 * wg + 16 * w + g) * 4));
      const float g1 = __uint_as_float(lds32(sb + OFF_GATE + (64 * wg + 16 * w + 8 + g) * 4));
      const uint32_t ga = pack2(g0, g0), gb = pack2(g1, g1);
      const uint32_t na = pack2(1.f - g0, 1.f - g0), nb = pack2(1.f - g1, 1.f - g1);

      uint32_t qf[20];
      mbar_wait(bars + 8 * B_QF, 0);
      TSM(w == 0 && wg == 0, 99);
#pragma unroll
      for (int j = 0; j < 5; j++) ldsm4(qf + 4 * j, QBOX ? fq + 32 * j : j < 4 ? fm + ((fx ^ (2 * j)) << 4) : ft);
      if (FUSE_MIX) {
#pragma unroll
        for (int i = 0; i < 20; i++) {
          qf[i] = bmul((i & 1) ? gb : ga, qf[i]);
          asm volatile("" : "+r"(qf[i]));
        }
      }
      wg_wait<0>();
      pin<40>(acc);
      TSM(w == 0, 17 + wg);
      uint32_t pb[20];
#pragma unroll
      for (int j = 0; j < 10; j++) {
        pb[2 * j] = bmul(na, pack2(acc[4 * j], acc[4 * j + 1]));
        pb[2 * j + 1] = bmul(nb, pack2(acc[4 * j + 2], acc[4 * j + 3]));
        asm volatile("" : "+r"(pb[2 * j]), "+r"(pb[2 * j + 1]));
      }
      const uint32_t ya = sb + OFF_YT + wg * 10240 + ((lane >> 4) * 8 + (lane & 7)) * 128 +
                          (((2 * w + (((lane >> 3) & 1) ^ wg)) ^ (lane & 7)) << 4);
      mbar_wait(bars + 8 * B_YFULL, 0);
      TSM(w == 0 && wg == 0, 19);
#pragma unroll
      for (int j = 0; j < 5; j++) {
        uint32_t y[4];
        ldsm4t(y, ya + 2048 * j);
#pragma unroll
        for (int i = 0; i < 4; i++)
          qf[4 * j + i] = FUSE_MIX ? bfma(qf[4 * j + i], y[i], pb[4 * j + i]) : badd(bmul((i & 1) ? gb : ga, bmul(qf[4 * j + i], y[i])), pb[4 * j + i]);
      }
#pragma unroll
      for (int j = 0; j < 5; j++) stsm4(QBOX ? fq + 32 * j : j < 4 ? fm + ((fx ^ (2 * j)) << 4) : ft, qf + 4 * j);
      fence_async_smem();
      __syncwarp();
      if (lane == 0) {
        const int row = 64 * wg + 16 * w;
        asm volatile("cp.async.bulk.tensor.2d.global.shared::cta.bulk_group [%0, {%2, %3}], [%1];"
                     ::"l"(&m.om), "r"(sb + OFF_QS + row * (QBOX ? 160 : 128)), "r"(80 * hg), "r"(128 * r + row) : "memory");
        if (!QBOX) asm volatile("cp.async.bulk.tensor.2d.global.shared::cta.bulk_group [%0, {%2, %3}], [%1];"
                     ::"l"(&m.ot), "r"(sb + OFF_QT + row * 32), "r"(80 * hg + 64), "r"(128 * r + row) : "memory");
        asm volatile("cp.async.bulk.commit_group;\ncp.async.bulk.wait_group.read 0;" ::: "memory");
      }
      TSM(w == 0 || w == 3, 40 + 2 * wg + (w & 1));
      if (ENDBAR) asm volatile("bar.sync 15, 256;" ::: "memory");
    }
  }
}

typedef CUresult (*EncodeFn)(CUtensorMap*, CUtensorMapDataType, cuuint32_t, void*, const cuuint64_t*, const cuuint64_t*,
                             const cuuint32_t*, const cuuint32_t*, CUtensorMapInterleave, CUtensorMapSwizzle,
                             CUtensorMapL2promotion, CUtensorMapFloatOOBfill);

void encode(EncodeFn fn, CUtensorMap* tm, const void* base, int rank, const cuuint64_t* dims, const cuuint64_t* strides,
            const cuuint32_t* box, CUtensorMapSwizzle swz) {
  const cuuint32_t ones[3] = {1, 1, 1};
  fn(tm, CU_TENSOR_MAP_DATA_TYPE_BFLOAT16, rank, const_cast<void*>(base), dims, strides, box, ones,
     CU_TENSOR_MAP_INTERLEAVE_NONE, swz, CU_TENSOR_MAP_L2_PROMOTION_L2_128B, CU_TENSOR_MAP_FLOAT_OOB_FILL_NONE);
}

}

extern "C" void kernel_launch(void* const* d_in, const int* in_sizes, int n_in, void* d_out, int out_size) {
  (void)in_sizes; (void)n_in; (void)out_size;
  Params p;
  p.q = (const __nv_bfloat16*)d_in[0];
  p.k = (const __nv_bfloat16*)d_in[1];
  p.v = (const __nv_bfloat16*)d_in[2];
  p.shift_k = (const __nv_bfloat16*)d_in[3];
  p.ssm_k = (const __nv_bfloat16*)d_in[4];
  p.ssm_D = (const __nv_bfloat16*)d_in[5];
  p.wqkv = (const __nv_bfloat16*)d_in[7];
  p.wo = (const __nv_bfloat16*)d_in[8];
  p.gate_w = (const __nv_bfloat16*)d_in[9];
  p.out = (__nv_bfloat16*)d_out;
  p.zero = 0;

  static EncodeFn fn = nullptr;
  static void *yaddr = nullptr, *uaddr = nullptr;
  if (!fn) {
    cudaDriverEntryPointQueryResult qr;
    void* f = nullptr;
    cudaGetDriverEntryPoint("cuTensorMapEncodeTiled", &f, cudaEnableDefault, &qr);
    fn = (EncodeFn)f;
    cudaGetSymbolAddress(&yaddr, g_Y);
    cudaGetSymbolAddress(&uaddr, g_U);
    cudaFuncSetAttribute(fused_kernel, cudaFuncAttributeMaxDynamicSharedMemorySize, SMEM_BYTES);
  }
  Maps m;
  {
    const cuuint64_t dims[3] = {640, 1024, 2}, st[2] = {2560, 1280};
    const cuuint32_t box[3] = {64, 64, 2};
    encode(fn, &m.x, p.q, 3, dims, st, box, CU_TENSOR_MAP_SWIZZLE_128B);
  }
  {
    const cuuint64_t dims[3] = {640, 640, 3}, st[2] = {3840, 1280};
    const cuuint32_t box[3] = {64, 64, 3}, boxt[3] = {16, 64, 3};
    encode(fn, &m.wm, p.wqkv, 3, dims, st, box, CU_TENSOR_MAP_SWIZZLE_128B);
    encode(fn, &m.wt, p.wqkv, 3, dims, st, boxt, CU_TENSOR_MAP_SWIZZLE_32B);
  }
  {
    const cuuint64_t dims[3] = {64, 2048, 10}, st[2] = {1280, 128};
    const cuuint32_t boxk[3] = {64, 35, 1}, boxv[3] = {64, 32, 1};
    encode(fn, &m.k, p.k, 3, dims, st, boxk, CU_TENSOR_MAP_SWIZZLE_128B);
    encode(fn, &m.v, p.v, 3, dims, st, boxv, CU_TENSOR_MAP_SWIZZLE_128B);
  }
  {
    const cuuint64_t dims[3] = {16, 640, 40}, st[2] = {1280, 32};
    const cuuint32_t box[3] = {16, 40, 5};
    encode(fn, &m.wo, p.wo, 3, dims, st, box, CU_TENSOR_MAP_SWIZZLE_32B);
  }
  {
    const cuuint64_t dims[2] = {2048, 640}, st[1] = {Y_PITCH * 16};
    const cuuint32_t box[2] = {64, 80};
    encode(fn, &m.y, yaddr, 2, dims, st, box, CU_TENSOR_MAP_SWIZZLE_128B);
    const cuuint64_t stu[1] = {U_PITCH * 16};
    const cuuint32_t boxu[2] = {32, 64};
    encode(fn, &m.u, uaddr, 2, dims, stu, boxu, CU_TENSOR_MAP_SWIZZLE_NONE);
  }
  {
    const cuuint64_t dims[2] = {640, 2048}, st[1] = {1280};
    const cuuint32_t bqm[2] = {QBOX ? 80 : 64, 128}, bqt[2] = {16, 128}, bom[2] = {QBOX ? 80 : 64, 16}, bot[2] = {16, 16};
    encode(fn, &m.qm, p.q, 2, dims, st, bqm, QBOX ? CU_TENSOR_MAP_SWIZZLE_NONE : CU_TENSOR_MAP_SWIZZLE_128B);
    encode(fn, &m.qt, p.q, 2, dims, st, bqt, CU_TENSOR_MAP_SWIZZLE_32B);
    encode(fn, &m.om, p.out, 2, dims, st, bom, QBOX ? CU_TENSOR_MAP_SWIZZLE_NONE : CU_TENSOR_MAP_SWIZZLE_128B);
    encode(fn, &m.ot, p.out, 2, dims, st, bot, CU_TENSOR_MAP_SWIZZLE_32B);
  }
  fused_kernel<<<NCTA, NTHR, SMEM_BYTES>>>(m, p);
}
```

```cpp
#include <cuda.h>
#include <cuda_bf16.h>
#include <cuda_runtime.h>
#include <stdint.h>

namespace {

constexpr int SEQ = 2048, DIM = 640, NCTA = 128, NTHR = 512;

#define TRIG_KB 9
#define KV_KB 2
#define DEV_EXIT 0
#define ATT_GATE 0
#define G_AFTER 0
#define FENCE_LO 0
#define FENCE_HI 0
#define PW1 2
#define PW2 1
#define ENDBAR 0
#define PAD_KB 0
#define Y_ALIAS 1
#define NOMB 0
#define SRC_ROT 0
#define WAIT_NS 0
#define WB_TRIG B_USIG
#define G_POS 0
#define TAILF 1
#define T_ISSUE 384
#define T_PF 416
#define T_INIT 448
#define ATT_MERGE 0
#define BMAP 1
#define PRE2 1
#define KV_MIX 0
#define O_DEFER 0
#define TASK0 0x3
#define TASK1 0x52
#define TASK2 0x41
#define HALO_FIRST 1
#define PREV_EARLY 0
#define Y_RB 2
#define O_RB 2
#define O_EAGER 1
#define OP_TRIG B_ATTN
#define U_TRIM 1
#define Q_SLOT 3
#define G_TMA 1
#define W_RB 1
#define WPF B_S3
#define WPF_LIN 1
#define O_SPLIT 1
#define WO_SKIP 1
#define Q_REG 1
#define Q_AT 0
#define Q_LATE 0
#define ACQ 0
#define U_TMA 0
#define U_GATE 0
#define RF_GATE 0
#define WO_TRIG B_WST
#define WL_TRIG B_WOP
#define WO_GATE 4

constexpr uint32_t STAGE_BYTES = 47104, ST_W = 16384, ST_WT = 40960;
constexpr uint32_t O_BYTES = 20480, WO_BYTES = 12800;
constexpr uint32_t OFF_OA = 0;
constexpr uint32_t OFF_QS = Q_SLOT * O_BYTES, OFF_QT = OFF_QS + 16384;
constexpr uint32_t OFF_WC = 81920;
constexpr uint32_t OFF_WA = 94720;
constexpr uint32_t OFF_GATE = 145920;
constexpr uint32_t OFF_TT = 146432;
constexpr uint32_t OFF_KVX = 148480;
constexpr uint32_t OFF_CH3 = 163840;
constexpr uint32_t CH_BYTES = 12288, U_BYTES = 4096;
constexpr uint32_t OFF_FT = 225280, OFF_GT = 229376;
constexpr uint32_t OFF_CH0 = 188416;
constexpr uint32_t OFF_KVS = OFF_CH0, KVS_V = 4480, KVS_BYTES = 8576;
constexpr uint32_t OFF_WS = OFF_WA;
__device__ __forceinline__ uint32_t off_us(int s) { return OFF_CH0 + 4096 * ((0x65320 >> (4 * s)) & 7); }
constexpr uint32_t OFF_YT = 163840;
constexpr uint32_t OFF_BAR = 231936;
constexpr uint32_t SMEM_BYTES = OFF_BAR + 512;

enum : uint32_t {
  B_FULL1 = 0, B_EMPTY1 = 4, B_S3 = 7, B_FULL2 = 52, B_EMPTY2 = 13, B_U = 8, B_GATE = 12, B_HA = 19, B_HB = 20,
  B_ATTN = 21, B_C34 = 22, B_YRB = 23, B_YFULL = 24, B_EPOCH = 25, B_PREP = 26, B_P1 = 27, B_LAST = 28,
  B_E3 = 29, B_OSIG = 30, B_WOP = 31, B_USIG = 32, B_WST = 33, B_KV = 34, B_KVD = 39, B_QF = 17, B_ATT2 = 18, B_YST = 40,
  B_ORB = 45, B_QE = 46, B_CVD = 33 + 14, B_US = 45, B_YSIG = 50
};
constexpr uint32_t OFF_EPOCH = OFF_BAR + 8 * 51, OFF_D = OFF_BAR + 8 * 60;
__device__ __forceinline__ uint32_t off_o(int j) { return j < 4 ? OFF_OA + j * O_BYTES : j < 6 ? OFF_CH0 + (j - 4) * O_BYTES : OFF_OA + (j - 6) * O_BYTES; }
__device__ __forceinline__ uint32_t off_w(int j) { return j < 4 ? OFF_WA + j * WO_BYTES : j == 4 ? OFF_KVX : j == 5 ? OFF_WC : OFF_WA + (j - 6) * WO_BYTES; }
__device__ __forceinline__ int step_src(int hg, int j) {
  if (SRC_ROT == 2) {
    const int pos = (0x37621540 >> (4 * hg)) & 7;
    return j == 0 ? hg : (0x65217430 >> (4 * (j <= pos ? j - 1 : j))) & 7;
  }
  return SRC_ROT ? (hg + j) & 7 : j == 0 ? hg : j <= hg ? j - 1 : j;
}
__device__ __forceinline__ bool tail_first(int hg) { return TAILF && (hg & 3) == 3; }
__device__ __forceinline__ uint32_t off_ch(int c) { return (c < 3 ? OFF_CH0 : OFF_CH3 - 3 * CH_BYTES) + c * CH_BYTES; }

#define U_PITCH 264
__device__ __align__(1024) uint4 g_U[DIM * U_PITCH];
__device__ uint4 g_O[NCTA * 1280];
#define g_Y g_U
constexpr int Y_PITCH = U_PITCH;
__device__ uint4 g_WO[64 * 800];
__device__ uint4 g_halo[NCTA * 2 * 7 * 32];
__device__ __align__(128) float g_gate[SEQ + PAD_KB * 256];
__device__ unsigned g_cnt[32 * (1 + 2 * 16 + 8 + NCTA)];
constexpr int C_LAUNCH = 0, C_PREP = 32, C_Y = 32 * 17, C_W = 32 * 33, C_O = 32 * 41;

#define TSM(cond, slot) do { } while (0)
#define TSIF(cond, slot) do { if (__LINE__ >= FENCE_LO && __LINE__ < FENCE_HI) sched_fence(); } while (0)
__device__ __forceinline__ void sched_fence() {
  asm volatile("{\n.reg .pred p;\n.reg .u32 c;\nmov.u32 c, %%clock;\nsetp.eq.u32 p, c, 0;\n@p st.shared.u32 [%0], c;\n}"
               ::"r"(1024 + OFF_EPOCH + 4) : "memory");
}
#define TS(slot) TSIF(true, slot)

struct Params {
  const __nv_bfloat16 *q, *k, *v, *shift_k, *ssm_k, *ssm_D, *wqkv, *wo, *gate_w;
  __nv_bfloat16* out;
  uint32_t zero;
};

#define POLL_NS 0
constexpr int SPIN_LIMIT = 1 << 17;

__device__ __forceinline__ void mbar_init(uint32_t bar, uint32_t count) {
  asm volatile("mbarrier.init.shared::cta.b64 [%0], %1;" ::"r"(bar), "r"(count) : "memory");
}
__device__ __forceinline__ void mbar_expect_tx(uint32_t bar, uint32_t bytes) {
  asm volatile("mbarrier.arrive.expect_tx.shared::cta.b64 _, [%0], %1;" ::"r"(bar), "r"(bytes) : "memory");
}
__device__ __forceinline__ void mbar_arrive(uint32_t bar) {
  asm volatile("mbarrier.arrive.shared::cta.b64 _, [%0];" ::"r"(bar) : "memory");
}
__device__ __forceinline__ void mbar_wait(uint32_t bar, uint32_t parity) {
  uint32_t ok;
  int spins = 0;
  do {
    if (WAIT_NS)
      asm volatile("{\n.reg .pred p;\nmbarrier.try_wait.parity.shared::cta.b64 p, [%1], %2, %3;\nselp.b32 %0, 1, 0, p;\n}"
                   : "=r"(ok) : "r"(bar), "r"(parity), "r"(WAIT_NS) : "memory");
    else
      asm volatile("{\n.reg .pred p;\nmbarrier.try_wait.parity.shared::cta.b64 p, [%1], %2;\nselp.b32 %0, 1, 0, p;\n}"
                   : "=r"(ok) : "r"(bar), "r"(parity) : "memory");
    if (++spins > SPIN_LIMIT) break;
  } while (!ok);
}
__device__ __forceinline__ unsigned flag_read(const unsigned* p) {
  unsigned v;
  asm volatile("ld.relaxed.gpu.global.u32 %0, [%1];" : "=r"(v) : "l"(p) : "memory");
  return v;
}
__device__ __forceinline__ void flag_poll(const unsigned* p, unsigned target) {
  unsigned v;
  int spins = 0;
  do {
    if (POLL_NS && spins) __nanosleep(POLL_NS);
    asm volatile("ld.relaxed.gpu.global.u32 %0, [%1];" : "=r"(v) : "l"(p) : "memory");
    if (++spins > SPIN_LIMIT) break;
  } while ((int)(v - target) < 0);
}
__device__ __forceinline__ void flag_wait(const unsigned* p, unsigned target) {
  flag_poll(p, target);
  if (ACQ) asm volatile("fence.acquire.gpu;\nfence.proxy.async.global;" ::: "memory");
}
__device__ __forceinline__ void flag_signal(unsigned* p, int n, int lane) {
  if (lane == 0) asm volatile("fence.release.gpu;" ::: "memory");
  __syncwarp();
  if (lane < n) asm volatile("red.relaxed.gpu.global.add.u32 [%0], 1;" ::"l"(p + 32 * lane) : "memory");
}
__device__ __forceinline__ void flag_bump(unsigned* p) {
  asm volatile("red.relaxed.gpu.global.add.u32 [%0], 1;" ::"l"(p) : "memory");
}
__device__ __forceinline__ void fence_async_smem() { asm volatile("fence.proxy.async.shared::cta;" ::: "memory"); }
__device__ __forceinline__ void wg_sync(int id) { asm volatile("bar.sync %0, 128;" ::"r"(id) : "memory"); }

__device__ __forceinline__ void tma_2d(uint32_t dst, const CUtensorMap* tm, int c0, int c1, uint32_t bar) {
  asm volatile("cp.async.bulk.tensor.2d.shared::cluster.global.mbarrier::complete_tx::bytes [%0], [%1, {%3, %4}], [%2];"
               ::"r"(dst), "l"(tm), "r"(bar), "r"(c0), "r"(c1) : "memory");
}
__device__ __forceinline__ void tma_3d(uint32_t dst, const CUtensorMap* tm, int c0, int c1, int c2, uint32_t bar) {
  asm volatile("cp.async.bulk.tensor.3d.shared::cluster.global.mbarrier::complete_tx::bytes [%0], [%1, {%3, %4, %5}], [%2];"
               ::"r"(dst), "l"(tm), "r"(bar), "r"(c0), "r"(c1), "r"(c2) : "memory");
}
__device__ __forceinline__ void bulk_load(uint32_t dst, const void* src, uint32_t bytes, uint32_t bar) {
  asm volatile("cp.async.bulk.shared::cluster.global.mbarrier::complete_tx::bytes [%0], [%1], %2, [%3];"
               ::"r"(dst), "l"(src), "r"(bytes), "r"(bar) : "memory");
}
__device__ __forceinline__ void bulk_store(void* dst, uint32_t src, uint32_t bytes) {
  asm volatile("cp.async.bulk.global.shared::cta.bulk_group [%0], [%1], %2;\ncp.async.bulk.commit_group;"
               ::"l"(dst), "r"(src), "r"(bytes) : "memory");
}
template <int N> __device__ __forceinline__ void bulk_wait_read() { asm volatile("cp.async.bulk.wait_group.read %0;" ::"n"(N) : "memory"); }
__device__ __forceinline__ void tm_prefetch(const CUtensorMap* tm) {
  asm volatile("prefetch.tensormap [%0];" ::"l"(tm) : "memory");
}

__device__ __forceinline__ void wg_fence() { asm volatile("wgmma.fence.sync.aligned;" ::: "memory"); }
__device__ __forceinline__ void wg_commit() { asm volatile("wgmma.commit_group.sync.aligned;" ::: "memory"); }
template <int N> __device__ __forceinline__ void wg_wait() { asm volatile("wgmma.wait_group.sync.aligned %0;" ::"n"(N) : "memory"); }
__device__ __forceinline__ uint32_t desc_lo(uint32_t addr, uint32_t lbo) { return ((addr & 0x3FFFF) >> 4) | ((lbo >> 4) << 16); }
constexpr uint32_t desc_hi(uint32_t sbo, uint32_t swz) { return (sbo >> 4) | (swz << 30); }
constexpr uint32_t HI_SW128 = desc_hi(1024, 1), HI_SW64 = desc_hi(512, 2), HI_SW32 = desc_hi(256, 3), HI_NONE = desc_hi(128, 0);
template <int N> __device__ __forceinline__ void pin(float* d) {
#pragma unroll
  for (int i = 0; i < N; i++) asm volatile("" : "+f"(d[i])::"memory");
}

__device__ __forceinline__ uint32_t lds32(uint32_t a) {
  uint32_t v;
  asm volatile("ld.volatile.shared.u32 %0, [%1];" : "=r"(v) : "r"(a) : "memory");
  return v;
}
__device__ __forceinline__ uint4 ldg128(const void* a) {
  uint4 v;
  asm volatile("ld.global.nc.v4.u32 {%0, %1, %2, %3}, [%4];" : "=r"(v.x), "=r"(v.y), "=r"(v.z), "=r"(v.w) : "l"(a) : "memory");
  return v;
}
__device__ __forceinline__ uint2 ldg64(const void* a) {
  uint2 v;
  asm volatile("ld.global.nc.v2.u32 {%0, %1}, [%2];" : "=r"(v.x), "=r"(v.y) : "l"(a) : "memory");
  return v;
}
__device__ __forceinline__ void ldsm4(uint32_t* r, uint32_t a) {
  asm volatile("ldmatrix.sync.aligned.m8n8.x4.shared.b16 {%0, %1, %2, %3}, [%4];"
               : "=r"(r[0]), "=r"(r[1]), "=r"(r[2]), "=r"(r[3]) : "r"(a) : "memory");
}
__device__ __forceinline__ void ldsm4t(uint32_t* r, uint32_t a) {
  asm volatile("ldmatrix.sync.aligned.m8n8.x4.trans.shared.b16 {%0, %1, %2, %3}, [%4];"
               : "=r"(r[0]), "=r"(r[1]), "=r"(r[2]), "=r"(r[3]) : "r"(a) : "memory");
}
__device__ __forceinline__ uint2 lds64(uint32_t a) {
  uint2 v;
  asm volatile("ld.shared.v2.u32 {%0, %1}, [%2];" : "=r"(v.x), "=r"(v.y) : "r"(a) : "memory");
  return v;
}
__device__ __forceinline__ uint4 lds128(uint32_t a) {
  uint4 v;
  asm volatile("ld.shared.v4.u32 {%0, %1, %2, %3}, [%4];" : "=r"(v.x), "=r"(v.y), "=r"(v.z), "=r"(v.w) : "r"(a) : "memory");
  return v;
}
__device__ __forceinline__ void sts128(uint32_t a, uint32_t x, uint32_t y, uint32_t z, uint32_t w) {
  asm volatile("st.shared.v4.u32 [%0], {%1, %2, %3, %4};" ::"r"(a), "r"(x), "r"(y), "r"(z), "r"(w) : "memory");
}
__device__ __forceinline__ void stsm4(uint32_t a, const uint32_t* r) {
  asm volatile("stmatrix.sync.aligned.m8n8.x4.shared.b16 [%0], {%1, %2, %3, %4};" ::"r"(a), "r"(r[0]), "r"(r[1]), "r"(r[2]), "r"(r[3]) : "memory");
}
__device__ __forceinline__ void stsm4t(uint32_t a, const uint32_t* r) {
  asm volatile("stmatrix.sync.aligned.m8n8.x4.trans.shared.b16 [%0], {%1, %2, %3, %4};" ::"r"(a), "r"(r[0]), "r"(r[1]), "r"(r[2]), "r"(r[3]) : "memory");
}
__device__ __forceinline__ uint32_t pack2(float lo, float hi) {
  uint32_t r;
  asm("cvt.rn.bf16x2.f32 %0, %1, %2;" : "=r"(r) : "f"(hi), "f"(lo));
  return r;
}
__device__ __forceinline__ uint32_t movm(uint32_t a) {
  uint32_t d;
  asm volatile("movmatrix.sync.aligned.m8n8.trans.b16 %0, %1;" : "=r"(d) : "r"(a));
  return d;
}
__device__ __forceinline__ uint32_t bmul(uint32_t a, uint32_t b) {
  uint32_t d;
  asm("mul.rn.bf16x2 %0, %1, %2;" : "=r"(d) : "r"(a), "r"(b));
  return d;
}
__device__ __forceinline__ uint32_t badd(uint32_t a, uint32_t b) {
  uint32_t d;
  asm("add.rn.bf16x2 %0, %1, %2;" : "=r"(d) : "r"(a), "r"(b));
  return d;
}
__device__ __forceinline__ uint32_t bfma(uint32_t a, uint32_t b, uint32_t c) {
  uint32_t d;
  asm("fma.rn.bf16x2 %0, %1, %2, %3;" : "=r"(d) : "r"(a), "r"(b), "r"(c));
  return d;
}
__device__ __forceinline__ float bf_lo(uint32_t x) { return __uint_as_float(x << 16); }
__device__ __forceinline__ float bf_hi(uint32_t x) { return __uint_as_float(x & 0xFFFF0000u); }
__device__ __forceinline__ float ex2(float x) {
  float y;
  asm("ex2.approx.ftz.f32 %0, %1;" : "=f"(y) : "f"(x));
  return y;
}
__device__ __forceinline__ float rcp(float x) {
  float y;
  asm("rcp.approx.ftz.f32 %0, %1;" : "=f"(y) : "f"(x));
  return y;
}
__device__ __forceinline__ void mma16816(float* d, uint32_t a0, uint32_t a1, uint32_t a2, uint32_t a3, uint32_t b0, uint32_t b1) {
  asm volatile("mma.sync.aligned.m16n8k16.row.col.f32.bf16.bf16.f32 {%0, %1, %2, %3}, {%4, %5, %6, %7}, {%8, %9}, {%0, %1, %2, %3};"
               : "+f"(d[0]), "+f"(d[1]), "+f"(d[2]), "+f"(d[3])
               : "r"(a0), "r"(a1), "r"(a2), "r"(a3), "r"(b0), "r"(b1));
}
__device__ __forceinline__ void mma1688(float* d, uint32_t a0, uint32_t a1, uint32_t b0) {
  asm volatile("mma.sync.aligned.m16n8k8.row.col.f32.bf16.bf16.f32 {%0, %1, %2, %3}, {%4, %5}, {%6}, {%0, %1, %2, %3};"
               : "+f"(d[0]), "+f"(d[1]), "+f"(d[2]), "+f"(d[3])
               : "r"(a0), "r"(a1), "r"(b0));
}

template <int N> struct WgRS;
template <int N> struct WgSST;
template <> struct WgRS<32> {
  template <uint32_t HB>
  static __device__ __forceinline__ void mma(float* d, const uint32_t* a, uint32_t db) {
    asm volatile("{\n.reg .pred p;\n.reg .b64 db;\nsetp.ne.b32 p, %22, 0;\n"
      "mov.b64 db, {%20, %21};\n"
      "wgmma.mma_async.sync.aligned.m64n32k16.f32.bf16.bf16 {"
      "%0, %1, %2, %3, %4, %5, %6, %7, %8, %9, %10, %11, %12, %13, %14, %15"
      "}, {%16, %17, %18, %19}, db, p, 1, 1, 1;\n}\n"
      : "+f"(d[0]), "+f"(d[1]), "+f"(d[2]), "+f"(d[3]), "+f"(d[4]), "+f"(d[5]), "+f"(d[6]), "+f"(d[7]),
        "+f"(d[8]), "+f"(d[9]), "+f"(d[10]), "+f"(d[11]), "+f"(d[12]), "+f"(d[13]), "+f"(d[14]), "+f"(d[15])
      : "r"(a[0]), "r"(a[1]), "r"(a[2]), "r"(a[3]), "r"(db), "n"(HB), "n"(1));
  }
  template <uint32_t HB>
  static __device__ __forceinline__ void set(float* d, const uint32_t* a, uint32_t db) {
    asm volatile("{\n.reg .pred p;\n.reg .b64 db;\nsetp.ne.b32 p, %22, 0;\n"
      "mov.b64 db, {%20, %21};\n"
      "wgmma.mma_async.sync.aligned.m64n32k16.f32.bf16.bf16 {"
      "%0, %1, %2, %3, %4, %5, %6, %7, %8, %9, %10, %11, %12, %13, %14, %15"
      "}, {%16, %17, %18, %19}, db, p, 1, 1, 1;\n}\n"
      : "=f"(d[0]), "=f"(d[1]), "=f"(d[2]), "=f"(d[3]), "=f"(d[4]), "=f"(d[5]), "=f"(d[6]), "=f"(d[7]),
        "=f"(d[8]), "=f"(d[9]), "=f"(d[10]), "=f"(d[11]), "=f"(d[12]), "=f"(d[13]), "=f"(d[14]), "=f"(d[15])
      : "r"(a[0]), "r"(a[1]), "r"(a[2]), "r"(a[3]), "r"(db), "n"(HB), "n"(0));
  }
};
template <> struct WgRS<64> {
  template <uint32_t HB>
  static __device__ __forceinline__ void mma(float* d, const uint32_t* a, uint32_t db) {
    asm volatile("{\n.reg .pred p;\n.reg .b64 db;\nsetp.ne.b32 p, %38, 0;\n"
      "mov.b64 db, {%36, %37};\n"
      "wgmma.mma_async.sync.aligned.m64n64k16.f32.bf16.bf16 {"
      "%0, %1, %2, %3, %4, %5, %6, %7, %8, %9, %10, %11, %12, %13, %14, %15, "
      "%16, %17, %18, %19, %20, %21, %22, %23, %24, %25, %26, %27, %28, %29, %30, %31"
      "}, {%32, %33, %34, %35}, db, p, 1, 1, 1;\n}\n"
      : "+f"(d[0]), "+f"(d[1]), "+f"(d[2]), "+f"(d[3]), "+f"(d[4]), "+f"(d[5]), "+f"(d[6]), "+f"(d[7]),
        "+f"(d[8]), "+f"(d[9]), "+f"(d[10]), "+f"(d[11]), "+f"(d[12]), "+f"(d[13]), "+f"(d[14]), "+f"(d[15]),
        "+f"(d[16]), "+f"(d[17]), "+f"(d[18]), "+f"(d[19]), "+f"(d[20]), "+f"(d[21]), "+f"(d[22]), "+f"(d[23]),
        "+f"(d[24]), "+f"(d[25]), "+f"(d[26]), "+f"(d[27]), "+f"(d[28]), "+f"(d[29]), "+f"(d[30]), "+f"(d[31])
      : "r"(a[0]), "r"(a[1]), "r"(a[2]), "r"(a[3]), "r"(db), "n"(HB), "n"(1));
  }
  template <uint32_t HB>
  static __device__ __forceinline__ void set(float* d, const uint32_t* a, uint32_t db) {
    asm volatile("{\n.reg .pred p;\n.reg .b64 db;\nsetp.ne.b32 p, %38, 0;\n"
      "mov.b64 db, {%36, %37};\n"
      "wgmma.mma_async.sync.aligned.m64n64k16.f32.bf16.bf16 {"
      "%0, %1, %2, %3, %4, %5, %6, %7, %8, %9, %10, %11, %12, %13, %14, %15, "
      "%16, %17, %18, %19, %20, %21, %22, %23, %24, %25, %26, %27, %28, %29, %30, %31"
      "}, {%32, %33, %34, %35}, db, p, 1, 1, 1;\n}\n"
      : "=f"(d[0]), "=f"(d[1]), "=f"(d[2]), "=f"(d[3]), "=f"(d[4]), "=f"(d[5]), "=f"(d[6]), "=f"(d[7]),
        "=f"(d[8]), "=f"(d[9]), "=f"(d[10]), "=f"(d[11]), "=f"(d[12]), "=f"(d[13]), "=f"(d[14]), "=f"(d[15]),
        "=f"(d[16]), "=f"(d[17]), "=f"(d[18]), "=f"(d[19]), "=f"(d[20]), "=f"(d[21]), "=f"(d[22]), "=f"(d[23]),
        "=f"(d[24]), "=f"(d[25]), "=f"(d[26]), "=f"(d[27]), "=f"(d[28]), "=f"(d[29]), "=f"(d[30]), "=f"(d[31])
      : "r"(a[0]), "r"(a[1]), "r"(a[2]), "r"(a[3]), "r"(db), "n"(HB), "n"(0));
  }
};
template <> struct WgSST<48> {
  template <uint32_t HA, uint32_t HB>
  static __device__ __forceinline__ void mma(float* d, uint32_t da, uint32_t db, int sc) {
    asm volatile("{\n.reg .pred p;\n.reg .b64 da, db;\nsetp.ne.b32 p, %28, 0;\n"
      "mov.b64 da, {%24, %25};\nmov.b64 db, {%26, %27};\n"
      "wgmma.mma_async.sync.aligned.m64n48k16.f32.bf16.bf16 {"
      "%0, %1, %2, %3, %4, %5, %6, %7, %8, %9, %10, %11, %12, %13, %14, %15, "
      "%16, %17, %18, %19, %20, %21, %22, %23"
      "}, da, db, p, 1, 1, 0, 1;\n}\n"
      : "+f"(d[0]), "+f"(d[1]), "+f"(d[2]), "+f"(d[3]), "+f"(d[4]), "+f"(d[5]), "+f"(d[6]), "+f"(d[7]),
        "+f"(d[8]), "+f"(d[9]), "+f"(d[10]), "+f"(d[11]), "+f"(d[12]), "+f"(d[13]), "+f"(d[14]), "+f"(d[15]),
        "+f"(d[16]), "+f"(d[17]), "+f"(d[18]), "+f"(d[19]), "+f"(d[20]), "+f"(d[21]), "+f"(d[22]), "+f"(d[23])
      : "r"(da), "n"(HA), "r"(db), "n"(HB), "r"(sc));
  }
};
template <> struct WgSST<80> {
  template <uint32_t HA, uint32_t HB>
  static __device__ __forceinline__ void mma(float* d, uint32_t da, uint32_t db, int sc) {
    asm volatile("{\n.reg .pred p;\n.reg .b64 da, db;\nsetp.ne.b32 p, %44, 0;\n"
      "mov.b64 da, {%40, %41};\nmov.b64 db, {%42, %43};\n"
      "wgmma.mma_async.sync.aligned.m64n80k16.f32.bf16.bf16 {"
      "%0, %1, %2, %3, %4, %5, %6, %7, %8, %9, %10, %11, %12, %13, %14, %15, "
      "%16, %17, %18, %19, %20, %21, %22, %23, %24, %25, %26, %27, %28, %29, %30, %31, "
      "%32, %33, %34, %35, %36, %37, %38, %39"
      "}, da, db, p, 1, 1, 0, 1;\n}\n"
      : "+f"(d[0]), "+f"(d[1]), "+f"(d[2]), "+f"(d[3]), "+f"(d[4]), "+f"(d[5]), "+f"(d[6]), "+f"(d[7]),
        "+f"(d[8]), "+f"(d[9]), "+f"(d[10]), "+f"(d[11]), "+f"(d[12]), "+f"(d[13]), "+f"(d[14]), "+f"(d[15]),
        "+f"(d[16]), "+f"(d[17]), "+f"(d[18]), "+f"(d[19]), "+f"(d[20]), "+f"(d[21]), "+f"(d[22]), "+f"(d[23]),
        "+f"(d[24]), "+f"(d[25]), "+f"(d[26]), "+f"(d[27]), "+f"(d[28]), "+f"(d[29]), "+f"(d[30]), "+f"(d[31]),
        "+f"(d[32]), "+f"(d[33]), "+f"(d[34]), "+f"(d[35]), "+f"(d[36]), "+f"(d[37]), "+f"(d[38]), "+f"(d[39])
      : "r"(da), "n"(HA), "r"(db), "n"(HB), "r"(sc));
  }
};
template <> struct WgSST<192> {
  template <uint32_t HA, uint32_t HB>
  static __device__ __forceinline__ void mma(float* d, uint32_t da, uint32_t db, int sc) {
    asm volatile("{\n.reg .pred p;\n.reg .b64 da, db;\nsetp.ne.b32 p, %100, 0;\n"
      "mov.b64 da, {%96, %97};\nmov.b64 db, {%98, %99};\n"
      "wgmma.mma_async.sync.aligned.m64n192k16.f32.bf16.bf16 {"
      "%0, %1, %2, %3, %4, %5, %6, %7, %8, %9, %10, %11, %12, %13, %14, %15, "
      "%16, %17, %18, %19, %20, %21, %22, %23, %24, %25, %26, %27, %28, %29, %30, %31, "
      "%32, %33, %34, %35, %36, %37, %38, %39, %40, %41, %42, %43, %44, %45, %46, %47, "
      "%48, %49, %50, %51, %52, %53, %54, %55, %56, %57, %58, %59, %60, %61, %62, %63, "
      "%64, %65, %66, %67, %68, %69, %70, %71, %72, %73, %74, %75, %76, %77, %78, %79, "
      "%80, %81, %82, %83, %84, %85, %86, %87, %88, %89, %90, %91, %92, %93, %94, %95"
      "}, da, db, p, 1, 1, 0, 1;\n}\n"
      : "+f"(d[0]), "+f"(d[1]), "+f"(d[2]), "+f"(d[3]), "+f"(d[4]), "+f"(d[5]), "+f"(d[6]), "+f"(d[7]),
        "+f"(d[8]), "+f"(d[9]), "+f"(d[10]), "+f"(d[11]), "+f"(d[12]), "+f"(d[13]), "+f"(d[14]), "+f"(d[15]),
        "+f"(d[16]), "+f"(d[17]), "+f"(d[18]), "+f"(d[19]), "+f"(d[20]), "+f"(d[21]), "+f"(d[22]), "+f"(d[23]),
        "+f"(d[24]), "+f"(d[25]), "+f"(d[26]), "+f"(d[27]), "+f"(d[28]), "+f"(d[29]), "+f"(d[30]), "+f"(d[31]),
        "+f"(d[32]), "+f"(d[33]), "+f"(d[34]), "+f"(d[35]), "+f"(d[36]), "+f"(d[37]), "+f"(d[38]), "+f"(d[39]),
        "+f"(d[40]), "+f"(d[41]), "+f"(d[42]), "+f"(d[43]), "+f"(d[44]), "+f"(d[45]), "+f"(d[46]), "+f"(d[47]),
        "+f"(d[48]), "+f"(d[49]), "+f"(d[50]), "+f"(d[51]), "+f"(d[52]), "+f"(d[53]), "+f"(d[54]), "+f"(d[55]),
        "+f"(d[56]), "+f"(d[57]), "+f"(d[58]), "+f"(d[59]), "+f"(d[60]), "+f"(d[61]), "+f"(d[62]), "+f"(d[63]),
        "+f"(d[64]), "+f"(d[65]), "+f"(d[66]), "+f"(d[67]), "+f"(d[68]), "+f"(d[69]), "+f"(d[70]), "+f"(d[71]),
        "+f"(d[72]), "+f"(d[73]), "+f"(d[74]), "+f"(d[75]), "+f"(d[76]), "+f"(d[77]), "+f"(d[78]), "+f"(d[79]),
        "+f"(d[80]), "+f"(d[81]), "+f"(d[82]), "+f"(d[83]), "+f"(d[84]), "+f"(d[85]), "+f"(d[86]), "+f"(d[87]),
        "+f"(d[88]), "+f"(d[89]), "+f"(d[90]), "+f"(d[91]), "+f"(d[92]), "+f"(d[93]), "+f"(d[94]), "+f"(d[95])
      : "r"(da), "n"(HA), "r"(db), "n"(HB), "r"(sc));
  }
};

struct FftConst {
  uint32_t f[2][4], fi[4][4];
  uint32_t ta[2][2], tb[2][2];
};
__device__ __forceinline__ void cis(int m, float scale, float& c, float& s) {
  const float a = (float)m * (-6.283185307179586f * scale);
  c = __cosf(a);
  s = __sinf(a);
}
__device__ __forceinline__ void fft_tables(uint32_t (&v)[12], int tw) {
  const int row = tw >> 2, ch = tw & 3;
#pragma unroll
  for (int i = 0; i < 4; i++) {
    float c[2], s[2], x[2];
#pragma unroll
    for (int e = 0; e < 2; e++) {
      cis((((32 * (8 * ch + 2 * i + e) + 15) * (4 * row - 63) + 2048) & 4095) - 2048, 1.f / 4096, c[e], s[e]);
      float gc, gs;
      cis((((row & 15) * (8 * (ch & 1) + 2 * i + e) + 8) & 15) - 8, 1.f / 16, gc, gs);
      x[e] = (row >> 4) == (ch >> 1) ? gc : (ch >> 1) ? gs : -gs;
    }
    v[i] = pack2(c[0] * 0.125f, c[1] * 0.125f);
    v[4 + i] = pack2(s[0] * 0.125f, s[1] * 0.125f);
    v[8 + i] = pack2(x[0], x[1]);
  }
#pragma unroll
  for (int i = 0; i < 12; i++) asm volatile("" : "+r"(v[i]));
}
__device__ __forceinline__ void fft_tables_store(const uint32_t (&v)[12], uint32_t sb, int tw) {
  const int row = tw >> 2;
  const uint32_t x = ((tw ^ (row >> 1)) & 3) << 4, a = sb + OFF_FT + (16 * (row >> 3) + (row & 7)) * 64 + x;
  sts128(a, v[0], v[1], v[2], v[3]);
  sts128(a + 512, v[4], v[5], v[6], v[7]);
  sts128(sb + OFF_GT + row * 64 + x, v[8], v[9], v[10], v[11]);
}
__device__ __forceinline__ void fft_twiddles(uint32_t (&v)[2], int tw) {
  float a[2], s[2];
#pragma unroll
  for (int i = 0; i < 2; i++) {
    float c;
    cis((2 * (2 * (tw & 3) + i) - 15) * (4 * (tw >> 2) - 63), 1.f / 4096, c, s[i]);
    a[i] = __fdividef(-s[i], 1.f + c);
  }
  v[0] = pack2(a[0], a[1]);
  v[1] = pack2(s[0], s[1]);
  asm volatile("" : "+r"(v[0]), "+r"(v[1]));
}
__device__ __forceinline__ void fft_matrices(FftConst& k, uint32_t sb, int w, int lane) {
  const uint32_t x = (lane >> 1) & 3;
  const uint2 t0 = lds64(sb + OFF_TT + 256 * w + 8 * lane), t1 = lds64(sb + OFF_TT + 256 * w + 8 * (lane ^ 3));
  k.ta[0][0] = t0.x;
  k.tb[0][0] = t0.y;
  k.ta[1][1] = __byte_perm(t1.x, 0, 0x1032);
  k.tb[1][1] = __byte_perm(t1.y, 0, 0x1032);
#pragma unroll
  for (int j = 0; j < 2; j++) {
    k.ta[1 - j][j] = k.ta[j][j] ^ 0x80008000u;
    k.tb[1 - j][j] = k.tb[j][j] ^ 0x80008000u;
    asm volatile("" : "+r"(k.ta[0][j]), "+r"(k.tb[0][j]), "+r"(k.ta[1][j]), "+r"(k.tb[1][j]));
  }
#pragma unroll
  for (int i = 0; i < 2; i++) {
    ldsm4(k.f[i], sb + OFF_FT + (16 * w + (lane & 15)) * 64 + (((2 * i + (lane >> 4)) ^ x) << 4));
    ldsm4t(k.fi[i], sb + OFF_FT + (32 * i + lane) * 64 + ((w ^ x) << 4));
#pragma unroll
    for (int j = 0; j < 4; j++) {
      k.fi[2 + i][j] = (j & 1) ? k.fi[i][j - 1] ^ 0x80008000u : k.fi[i][j + 1];
      asm volatile("" : "+r"(k.fi[2 + i][j]));
    }
  }
}
__device__ __forceinline__ void rot(uint32_t& x, uint32_t& y, uint32_t a, uint32_t b) {
  x = bfma(a, y, x);
  y = bfma(b, x, y);
  x = bfma(a, y, x);
}
__device__ __forceinline__ void twiddle_fwd(uint32_t (&a)[4][4], float* d, const FftConst& k) {
#pragma unroll
  for (int q = 0; q < 4; q++)
#pragma unroll
    for (int j = 0; j < 2; j++) {
      const float* x = d + 8 * q + 4 * j;
      uint32_t re = pack2(x[0], x[1]), im = pack2(x[2], x[3]);
      rot(re, im, k.ta[0][j], k.tb[0][j]);
      a[q & 2][2 * j + (q & 1)] = re;
      a[(q & 2) + 1][2 * j + (q & 1)] = im;
    }
}
__device__ __forceinline__ void g_step(float* d, const uint32_t (&a)[4][4], uint32_t dre, uint32_t dim) {
  WgRS<32>::set<HI_SW64>(d, a[0], dre);
  WgRS<32>::set<HI_SW64>(d + 16, a[2], dre);
  WgRS<32>::mma<HI_SW64>(d, a[1], dim);
  WgRS<32>::mma<HI_SW64>(d + 16, a[3], dim);
  wg_commit();
}

__device__ __forceinline__ void products(uint32_t (&a)[4][4], const float* H, const float* U, int p) {
#pragma unroll
  for (int j = 0; j < 2; j++)
#pragma unroll
    for (int m = 2 * p; m < 2 * p + 2; m++) {
      float pr[2], pi[2];
#pragma unroll
      for (int x = 0; x < 2; x++)
#pragma unroll
        for (int q = 0; q <= m; q++) {
          const int ih = 16 * (q >> 1) + 2 * (q & 1) + 4 * j + x, iu = 16 * ((m - q) >> 1) + 2 * ((m - q) & 1) + 4 * j + x;
          pr[x] = q ? fmaf(H[ih], U[iu], pr[x]) : H[ih] * U[iu];
          pi[x] = q ? fmaf(H[ih], U[iu + 8], pi[x]) : H[ih] * U[iu + 8];
          pr[x] = fmaf(-H[ih + 8], U[iu + 8], pr[x]);
          pi[x] = fmaf(H[ih + 8], U[iu], pi[x]);
        }
      a[m & 2][2 * j + (m & 1)] = pack2(pr[0], pr[1]);
      a[(m & 2) + 1][2 * j + (m & 1)] = pack2(pi[0], pi[1]);
    }
}

__device__ __forceinline__ void f_step(float* d, const FftConst& k, uint32_t db) {
  WgRS<64>::set<HI_SW32>(d, k.f[0], db);
  WgRS<64>::mma<HI_SW32>(d, k.f[1], db + 32);
  wg_commit();
}
__device__ __forceinline__ void last_step(float* d, const FftConst& k, uint32_t dz) {
  wg_fence();
  WgRS<64>::set<HI_SW128>(d, k.fi[0], dz);
#pragma unroll
  for (int ks = 1; ks < 4; ks++) WgRS<64>::mma<HI_SW128>(d, k.fi[ks], dz + 128 * ks);
  wg_commit();
}
__device__ __forceinline__ void conv_channel(const FftConst& k, uint32_t (&a)[4][4], uint32_t sb, int c, int cn, int wg, int w, int lane) {
  const uint32_t cb = sb + off_ch(c), bars = sb + OFF_BAR;
  const uint32_t du = desc_lo(cb, 1024), dg = desc_lo(sb + OFF_GT, 16), dz = desc_lo(cb + U_BYTES, 16);
  float U[32], H[32];
  uint32_t e[4][4];
  const float dv = __uint_as_float(lds32(sb + OFF_D + 4 * c));
  if (ATT_GATE) mbar_wait(bars + 8 * (ATT_GATE == 1 ? B_ATTN : B_ATT2), 0);
  mbar_wait(bars + 8 * (B_U + (c < 3 ? c : 3)), 0);
  TSM(w == 0 && c < 3, 7 + wg);
  wg_fence();
  f_step(U, k, du);
  g_step(H, a, dg, dg + 64);
  wg_wait<1>();
  pin<32>(U);
  twiddle_fwd(e, U, k);
  wg_fence();
  g_step(U, e, dg, dg + 64);
  wg_wait<0>();
  pin<32>(U);
  pin<32>(H);
#pragma unroll
  for (int j = 0; j < 4; j++) H[4 * (j >> 1) + (j & 1)] += dv;
  float V[32];
#pragma unroll
  for (int p = 0; p < 2; p++) {
    products(a, H, U, p);
    wg_fence();
    WgRS<32>::set<HI_SW64>(V + 16 * p, a[2 * p], dg + 64);
    WgRS<32>::mma<HI_SW64>(V + 16 * p, a[2 * p + 1], dg);
    wg_commit();
  }
  const uint32_t za = cb + U_BYTES + (8 * w + (lane & 7)) * 128 + (((lane >> 3) ^ (lane & 7)) << 4);
  const uint32_t ya = cb + (lane >> 4) * 1024 + (8 * w + (lane & 7)) * 32 + ((((lane >> 3) ^ (lane >> 2)) & 1) << 4);
  wg_sync(1 + wg);
#pragma unroll
  for (int p = 0; p < 2; p++) {
    if (p == 0) wg_wait<1>();
    else wg_wait<0>();
    pin<16>(V + 16 * p);
#pragma unroll
    for (int i = 0; i < 4; i++) {
      const int j = i & 1;
      const float* x = V + 16 * p + 4 * j + (i & 2);
      e[p][i] = pack2(x[8], x[9]);
      e[2 + p][i] = pack2(x[0], x[1]);
      rot(e[p][i], e[2 + p][i], k.ta[1][j], k.tb[1][j]);
    }
    stsm4(za ^ (64 * p), e[p]);
    stsm4((za ^ (64 * p)) + 4096, e[2 + p]);
  }
  if (cn >= 0) {
    wg_fence();
    f_step(U, k, desc_lo(sb + off_ch(cn) + U_BYTES, 1024));
    fence_async_smem();
    wg_sync(1 + wg);
    last_step(H, k, dz);
    wg_wait<1>();
    pin<32>(U);
    twiddle_fwd(a, U, k);
    wg_wait<0>();
  } else {
    fence_async_smem();
    wg_sync(1 + wg);
    last_step(H, k, dz);
    wg_wait<0>();
  }
  pin<32>(H);
  if (WO_GATE == 4 && lane == 0) mbar_arrive(bars + 8 * B_CVD);
  TSIF(w == 0, 88 + c);
#pragma unroll
  for (int j = 0; j < 8; j++)
    e[j >> 2][j & 3] = j < 2 ? pack2(H[4 * j], H[4 * j + 1]) : pack2(H[4 * j] + H[4 * j - 6], H[4 * j + 1] + H[4 * j - 5]);
  stsm4(ya, e[0]);
  stsm4(ya + 2048, e[1]);
  fence_async_smem();
  __syncwarp();
}

__device__ __forceinline__ void prep_slab(uint4* res, const uint2* sw, uint32_t sb, int slab, int w, int lane) {
  const int t = lane & 3, tp = (lane & 7) >> 1, pos = 8 * tp + 2 * (((lane >> 3) + tp) & 3) + (lane & 1);
  const uint32_t base = sb + OFF_KVS + slab * KVS_BYTES + pos * 128;
  uint32_t kk[2][4][4], vv[2][4];
  mbar_wait(sb + OFF_BAR + 8 * (B_KV + slab), 0);
#pragma unroll
  for (int h = 0; h < 2; h++) {
#pragma unroll
    for (int j = 0; j < 4; j++) {
      const uint32_t a = base + 128 * j;
      ldsm4t(kk[h][j], a + (((w + 4 * h) ^ ((a >> 7) & 7)) << 4));
    }
    const uint32_t a = base + KVS_V;
    ldsm4t(vv[h], a + (((w + 4 * h) ^ ((a >> 7) & 7)) << 4));
  }
#pragma unroll
  for (int h = 0; h < 2; h++) {
    uint32_t (&k)[4][4] = kk[h];
    uint32_t (&v)[4] = vv[h];
    const uint32_t w0 = __byte_perm(sw[h].x, 0, 0x1010), w1 = __byte_perm(sw[h].x, 0, 0x3232);
    const uint32_t w2 = __byte_perm(sw[h].y, 0, 0x1010), w3 = __byte_perm(sw[h].y, 0, 0x3232);
#pragma unroll
    for (int m = 0; m < 4; m++)
      v[m] = bmul(badd(badd(badd(bmul(k[0][m], w3), bmul(k[1][m], w2)), bmul(k[2][m], w1)), bmul(k[3][m], w0)), v[m]);
    uint32_t a[4];
#pragma unroll
    for (int m = 0; m < 4; m++) a[m] = (t & 1) ? v[(m + 3) & 3] : v[m];
    res[h] = (t & 2) ? make_uint4(a[2], a[3], a[0], a[1]) : make_uint4(a[0], a[1], a[2], a[3]);
  }
}

__device__ __forceinline__ void prep_gate(const Params& p, uint32_t sb, int b, int w, int lane) {
  uint2 gw[5], x[4][5];
#pragma unroll
  for (int j = 0; j < 5; j++) gw[j] = ldg64(reinterpret_cast<const uint2*>(p.gate_w) + lane + 32 * j);
#pragma unroll
  for (int i = 0; i < 4; i++)
#pragma unroll
    for (int j = 0; j < 5; j++)
      x[i][j] = ldg64(reinterpret_cast<const uint2*>(p.q) + (16 * b + 4 * w + i) * (DIM / 4) + lane + 32 * j);
  float s[4];
#pragma unroll
  for (int i = 0; i < 4; i++) {
    s[i] = 0.f;
#pragma unroll
    for (int j = 0; j < 5; j++) {
      const uint32_t m0 = bmul(x[i][j].x, gw[j].x), m1 = bmul(x[i][j].y, gw[j].y);
      s[i] += (bf_lo(m0) + bf_hi(m0)) + (bf_lo(m1) + bf_hi(m1));
    }
  }
  const bool h = lane & 16, q = lane & 8;
  const float a = (h ? s[2] : s[0]) + __shfl_xor_sync(0xffffffffu, h ? s[0] : s[2], 16);
  const float c = (h ? s[3] : s[1]) + __shfl_xor_sync(0xffffffffu, h ? s[1] : s[3], 16);
  float z = (q ? c : a) + __shfl_xor_sync(0xffffffffu, q ? a : c, 8);
#pragma unroll
  for (int o = 4; o > 0; o >>= 1) z += __shfl_xor_sync(0xffffffffu, z, o);
  z = bf_lo(pack2(z, 0.f));
  z = bf_lo(pack2(__fdividef(1.f, 1.f + __expf(-z)), 0.f));
  if (G_TMA) {
    mbar_wait(sb + OFF_BAR + 8 * B_S3, 0);
    if ((lane & 7) == 0) asm volatile("st.shared.f32 [%0], %1;" ::"r"(sb + OFF_GATE + 64 * (b & 7) + 16 * w + (lane >> 1)), "f"(z) : "memory");
    fence_async_smem();
  } else if ((lane & 7) == 0) {
    g_gate[16 * b + 4 * w + (lane >> 3)] = z;
  }
}

__device__ __forceinline__ uint32_t bmax(uint32_t a, uint32_t b) {
  uint32_t d;
  asm("max.bf16x2 %0, %1, %2;" : "=r"(d) : "r"(a), "r"(b));
  return d;
}
__device__ __forceinline__ void softmax_two(const float (&l)[2][2], uint32_t& p0, uint32_t& p1) {
  constexpr float kScale = 0.22360679774997896f, kLog2e = 1.4426950408889634f;
  const uint32_t r0 = pack2(l[0][0], l[1][0]), r1 = pack2(l[0][1], l[1][1]);
  const uint32_t x0 = pack2(bf_lo(r0) * kScale, bf_hi(r0) * kScale), x1 = pack2(bf_lo(r1) * kScale, bf_hi(r1) * kScale);
  uint32_t m = bmax(x0, x1);
  m = bmax(m, __shfl_xor_sync(0xffffffffu, m, 1));
  m = bmax(m, __shfl_xor_sync(0xffffffffu, m, 2));
  const float m0 = bf_lo(m) * kLog2e, m1 = bf_hi(m) * kLog2e;
  p0 = pack2(ex2(bf_lo(x0) * kLog2e - m0), ex2(bf_lo(x1) * kLog2e - m0));
  p1 = pack2(ex2(bf_hi(x0) * kLog2e - m1), ex2(bf_hi(x1) * kLog2e - m1));
}

__device__ __forceinline__ void halo_read(uint32_t (&kpv)[10], uint32_t (&vpv)[10], uint32_t (&tg)[7], const uint4* hp) {
#pragma unroll
  for (int j = 0; j < 7; j++) {
    uint32_t x0, x1, x2;
    asm volatile("ld.relaxed.gpu.global.v4.u32 {%0, %1, %2, %3}, [%4];"
                 : "=r"(x0), "=r"(x1), "=r"(x2), "=r"(tg[j]) : "l"(hp + 32 * j) : "memory");
    if (j < 4) kpv[3 * j] = x0; else vpv[3 * j - 10] = x0;
    if (j < 3) kpv[3 * j + 1] = x1; else vpv[3 * j - 9] = x1;
    if (j < 3) kpv[3 * j + 2] = x2; else if (j < 6) vpv[3 * j - 8] = x2;
  }
}

template <int ROT>
__device__ __forceinline__ void pack_qkv(const float* acc, uint32_t (&qlo)[10], uint32_t (&qhi)[10], uint32_t (&klo)[10],
                                         uint32_t (&khi)[10], uint32_t (&vlo)[10], uint32_t (&vhi)[10]) {
#pragma unroll
  for (int j = 0; j < 10; j++) {
    const int x = (j + ROT) % 10, tq = x < 8 ? x : 16 + x, tk = x < 8 ? 8 + x : 18 + x, tv = x < 8 ? 16 + x : 20 + x;
    khi[j] = pack2(acc[4 * tk + 2], acc[4 * tk + 3]);
    vhi[j] = movm(pack2(acc[4 * tv + 2], acc[4 * tv + 3]));
    qlo[j] = pack2(acc[4 * tq], acc[4 * tq + 1]);
    qhi[j] = pack2(acc[4 * tq + 2], acc[4 * tq + 3]);
    klo[j] = pack2(acc[4 * tk], acc[4 * tk + 1]);
    vlo[j] = pack2(acc[4 * tv], acc[4 * tv + 1]);
    asm volatile("" : "+r"(khi[j]), "+r"(qlo[j]), "+r"(qhi[j]), "+r"(klo[j]), "+r"(vlo[j]));
  }
}

template <int ROT> __device__ __forceinline__ void halo_send(const float* acc, uint4* ho, uint32_t tag) {
#pragma unroll
  for (int j = 0; j < 7; j++) {
    uint32_t x[3];
#pragma unroll
    for (int e = 0; e < 3; e++) {
      const int i = 3 * j + e, y = (i % 10 + ROT) % 10, tk = y < 8 ? 8 + y : 18 + y, tv = y < 8 ? 16 + y : 20 + y;
      x[e] = i < 10 ? pack2(acc[4 * tk + 2], acc[4 * tk + 3]) : i < 20 ? movm(pack2(acc[4 * tv + 2], acc[4 * tv + 3])) : 0u;
    }
    asm volatile("st.relaxed.gpu.global.v4.u32 [%0], {%1, %2, %3, %4};" ::"l"(ho + 32 * j), "r"(x[0]), "r"(x[1]), "r"(x[2]), "r"(tag) : "memory");
  }
}

__device__ __forceinline__ void attention(float* acc, uint32_t sb, int b, int par, int w, int lane, uint32_t tag, uint32_t zero) {
  const int g = lane >> 2, t = lane & 3;
  uint32_t klo[10], khi[10], vlo[10], vhi[10], qlo[10], qhi[10], kpv[10], vpv[10];
  if (HALO_FIRST && w == 3 && b < NCTA - 8) {
    uint4* ho = g_halo + (b * 2 + par) * 224 + lane;
    if (tail_first(b & 7)) halo_send<8>(acc, ho, tag);
    else halo_send<0>(acc, ho, tag);
    TSIF(par == 0, 76);
    pin<120>(acc);
  }
  if (tail_first(b & 7)) pack_qkv<8>(acc, qlo, qhi, klo, khi, vlo, vhi);
  else pack_qkv<0>(acc, qlo, qhi, klo, khi, vlo, vhi);
  const uint32_t xa = sb + OFF_KVX + (par * 3) * 2560 + lane * 16;
  if (w < 3) {
    sts128(xa + w * 2560, khi[0], khi[1], khi[2], khi[3]);
    sts128(xa + w * 2560 + 512, khi[4], khi[5], khi[6], khi[7]);
    sts128(xa + w * 2560 + 1024, khi[8], khi[9], vhi[0], vhi[1]);
    sts128(xa + w * 2560 + 1536, vhi[2], vhi[3], vhi[4], vhi[5]);
    sts128(xa + w * 2560 + 2048, vhi[6], vhi[7], vhi[8], vhi[9]);
  } else if (!HALO_FIRST && b < NCTA - 8) {
    uint4* ho = g_halo + (b * 2 + par) * 224 + lane;
#pragma unroll
    for (int j = 0; j < 7; j++) {
      const uint32_t x0 = j < 4 ? khi[3 * j] : vhi[3 * j - 10], x1 = j < 3 ? khi[3 * j + 1] : vhi[3 * j - 9];
      const uint32_t x2 = j < 3 ? khi[3 * j + 2] : j < 6 ? vhi[3 * j - 8] : 0u;
      asm volatile("st.relaxed.gpu.global.v4.u32 [%0], {%1, %2, %3, %4};" ::"l"(ho + 32 * j), "r"(x0), "r"(x1), "r"(x2), "r"(tag) : "memory");
    }
  }
  TSIF(par == 0 && w == 1, 64);
  TSIF(par == 0 && w == 3 && !HALO_FIRST, 76);
#pragma unroll
  for (int j = 0; j < 10; j++) vlo[j] = movm(vlo[j]);
  const bool far0 = 2 * t > g, far1 = 2 * t + 1 > g;
  const uint32_t mfar = (far0 ? 0x0000FFFFu : 0u) | (far1 ? 0xFFFF0000u : 0u);
  float slo[4][2], shi[4][2], lg[2][2];
  uint32_t phi[4], plo[4], qml[4], qmh[4];
#pragma unroll
  for (int h = 0; h < 4; h++) {
    const int f = h == 0 ? 0 : h == 1 ? 3 : h == 2 ? 5 : 8, hf = h < 2 ? 2 : 7;
    const bool mine = (h & 1) ? t >= 2 : t < 2;
    qml[h] = mine ? qlo[hf] : 0u;
    qmh[h] = mine ? qhi[hf] : 0u;
    float a[4] = {0.f, 0.f, 0.f, 0.f}, c[4] = {0.f, 0.f, 0.f, 0.f};
    mma16816(a, qlo[f], qhi[f], qlo[f + 1], qhi[f + 1], klo[f], klo[f + 1]);
    mma16816(c, qlo[f], qhi[f], qlo[f + 1], qhi[f + 1], khi[f], khi[f + 1]);
    mma1688(a, qml[h], qmh[h], klo[hf]);
    mma1688(c, qml[h], qmh[h], khi[hf]);
    slo[h][0] = a[0];
    slo[h][1] = a[1];
    shi[h][0] = lg[h & 1][0] = far0 ? a[2] : c[2];
    shi[h][1] = lg[h & 1][1] = far1 ? a[3] : c[3];
    if (!ATT_MERGE && (h & 1)) softmax_two(lg, phi[h - 1], phi[h]);
  }
  TSIF(par == 0 && w == 1, 65);
  if (ATT_GATE == 3 && lane == 0) mbar_arrive(sb + OFF_BAR + 8 * B_ATT2 + (phi[3] & zero));
  wg_sync(1 + par);
  TSIF(par == 0 && w == 1, 66);
  const bool nohist = (w == 0) && (b < 8);
  const uint4* hp = g_halo + ((b - 8) * 2 + par) * 224 + lane;
  uint32_t tg[7];
  if (w > 0) {
    const uint4 v0 = lds128(xa + (w - 1) * 2560), v1 = lds128(xa + (w - 1) * 2560 + 512), v2 = lds128(xa + (w - 1) * 2560 + 1024);
    const uint4 v3 = lds128(xa + (w - 1) * 2560 + 1536), v4 = lds128(xa + (w - 1) * 2560 + 2048);
    kpv[0] = v0.x; kpv[1] = v0.y; kpv[2] = v0.z; kpv[3] = v0.w; kpv[4] = v1.x; kpv[5] = v1.y; kpv[6] = v1.z; kpv[7] = v1.w;
    kpv[8] = v2.x; kpv[9] = v2.y; vpv[0] = v2.z; vpv[1] = v2.w; vpv[2] = v3.x; vpv[3] = v3.y; vpv[4] = v3.z; vpv[5] = v3.w;
    vpv[6] = v4.x; vpv[7] = v4.y; vpv[8] = v4.z; vpv[9] = v4.w;
  } else if (nohist) {
#pragma unroll
    for (int j = 0; j < 10; j++) kpv[j] = vpv[j] = 0u;
  } else {
    TSIF(par == 0, 77);
    halo_read(kpv, vpv, tg, hp);
  }
  if (w == 0 && !nohist) {
    int spins = 0;
    while (true) {
      bool ok = true;
#pragma unroll
      for (int j = 0; j < 7; j++) ok = ok && tg[j] == tag;
      if (__all_sync(0xffffffffu, ok) || ++spins > SPIN_LIMIT) break;
      halo_read(kpv, vpv, tg, hp);
    }
    TSIF(par == 0, 79);
  }
#pragma unroll
  for (int h = 0; h < 4; h++) {
    const int f = h == 0 ? 0 : h == 1 ? 3 : h == 2 ? 5 : 8, hf = h < 2 ? 2 : 7;
    float a[4] = {0.f, 0.f, 0.f, 0.f};
    mma16816(a, qlo[f], qhi[f], qlo[f + 1], qhi[f + 1], kpv[f], kpv[f + 1]);
    mma1688(a, qml[h], qmh[h], kpv[hf]);
    const float ninf = __int_as_float(0xff800000);
    lg[h & 1][0] = far0 ? (nohist ? ninf : a[0]) : slo[h][0];
    lg[h & 1][1] = far1 ? (nohist ? ninf : a[1]) : slo[h][1];
    if (h & 1) {
      softmax_two(lg, plo[h - 1], plo[h]);
      if (ATT_MERGE) {
        const float lh[2][2] = {{shi[h - 1][0], shi[h - 1][1]}, {shi[h][0], shi[h][1]}};
        softmax_two(lh, phi[h - 1], phi[h]);
      }
    }
  }
  TSIF(par == 0 && w <= 1, 67 + w);
  if (ATT_GATE == 2 && lane == 0) mbar_arrive(sb + OFF_BAR + 8 * B_ATT2 + (plo[3] & zero));
  uint32_t ov[20];
#pragma unroll
  for (int hp = 0; hp < 2; hp++) {
    const int hf = hp ? 7 : 2;
    float sh[4] = {0.f, 0.f, 0.f, 0.f}, i0 = 0.f, i1 = 0.f;
#pragma unroll
    for (int e = 0; e < 2; e++) {
      const int h = 2 * hp + e, f = h == 0 ? 0 : h == 1 ? 3 : h == 2 ? 5 : 8;
      const uint32_t a0 = plo[h] & mfar, a2 = plo[h] & ~mfar, a3 = phi[h] & mfar, c1 = phi[h] & ~mfar;
      float sum[4] = {0.f, 0.f, 0.f, 0.f};
      mma1688(sum, plo[h], phi[h], 0x3F803F80u);
      const float r0 = rcp(sum[0]), r1 = rcp(sum[2]);
#pragma unroll
      for (int j = f; j < f + 2; j++) {
        float o[4] = {0.f, 0.f, 0.f, 0.f};
        mma16816(o, a0, 0u, a2, a3, vpv[j], vlo[j]);
        mma1688(o, 0u, c1, vhi[j]);
        ov[2 * j] = pack2(o[0] * r0, o[1] * r0);
        ov[2 * j + 1] = pack2(o[2] * r1, o[3] * r1);
      }
      const bool mine = e ? g >= 4 : g < 4;
      mma16816(sh, a0, 0u, a2, a3, mine ? vpv[hf] : 0u, mine ? vlo[hf] : 0u);
      mma1688(sh, 0u, c1, mine ? vhi[hf] : 0u);
      if (e == 0 || t >= 2) {
        i0 = r0;
        i1 = r1;
      }
    }
    ov[2 * hf] = pack2(sh[0] * i0, sh[1] * i0);
    ov[2 * hf + 1] = pack2(sh[2] * i1, sh[3] * i1);
  }
  if (ATT_GATE == 4 && lane == 0) mbar_arrive(sb + OFF_BAR + 8 * B_ATT2 + (ov[19] & zero));
  TS(32 + 4 * par + w);
  mbar_wait(sb + OFF_BAR + 8 * B_P1, 0);
  const uint32_t oa = sb + OFF_OA + (lane >> 4) * 2048 + (32 * w + 2 * (lane & 15) + par) * 16;
#pragma unroll
  for (int j = 0; j < 5; j++) stsm4(oa + 4096 * j, ov + 4 * j);
  TSIF(par == 0 && w == 0, 120);
  fence_async_smem();
  TSIF(par == 0 && w == 0, 121);
  __syncwarp();
  if (lane == 0) mbar_arrive(sb + OFF_BAR + 8 * B_ATTN);
  TSM(w == 0 || w == 2, 122 + par + (w == 2 ? 3 : 0));
}

struct Maps {
  CUtensorMap x, wm, wt, k, v, y, wo, qm, qt, om, ot, u;
};

__device__ __forceinline__ void load_stage(uint32_t sb, int kb, int b, const Maps& m) {
  const uint32_t st = sb + (kb & 3) * STAGE_BYTES, bar = sb + OFF_BAR + 8 * (B_FULL1 + (kb & 3));
  const int r = b >> 3, hg = b & 7, slab = kb - KV_KB;
  const bool kv = slab >= 0 && slab < 5;
  const uint32_t kbar = sb + OFF_BAR + 8 * (B_KV + slab), dst = sb + OFF_KVS + slab * KVS_BYTES;
  mbar_expect_tx(bar, STAGE_BYTES);
  if (kv) mbar_expect_tx(kbar, KVS_BYTES);
  tma_3d(st, &m.x, 64 * kb, 64 * r, 0, bar);
  if (kv && KV_MIX) tma_3d(dst, &m.k, 0, 32 * (b >> 1) - 3, 2 * slab + (b & 1), kbar);
  tma_3d(st + ST_W, &m.wm, 80 * hg + (tail_first(hg) ? 16 : 0), 64 * kb, 0, bar);
  if (kv && KV_MIX) tma_3d(dst + KVS_V, &m.v, 0, 32 * (b >> 1), 2 * slab + (b & 1), kbar);
  tma_3d(st + ST_WT, &m.wt, 80 * hg + (tail_first(hg) ? 0 : 64), 64 * kb, 0, bar);
  if (kv && !KV_MIX) tma_3d(dst, &m.k, 0, 32 * (b >> 1) - 3, 2 * slab + (b & 1), kbar);
  if (kv && !KV_MIX) tma_3d(dst + KVS_V, &m.v, 0, 32 * (b >> 1), 2 * slab + (b & 1), kbar);
}

__global__ void __launch_bounds__(NTHR, 1) fused_kernel(const __grid_constant__ Maps m, const Params p) {
  extern __shared__ __align__(1024) uint8_t smem[];
  const uint32_t sb = (uint32_t)__cvta_generic_to_shared(smem);
  const uint32_t bars = sb + OFF_BAR;
  const int tid = threadIdx.x, lane = tid & 31;
  int b = blockIdx.x;
  if (BMAP == 1) b = (((b & 63) >> 3) * 2 + (b & 1)) * 8 + (((b < 64 ? 0x6521 : 0x7430) >> (4 * ((b >> 1) & 3))) & 7);
  if (BMAP == 2) b = ((b & 63) >> 2) * 8 + (((b < 64 ? 0x6521 : 0x7430) >> (4 * (b & 3))) & 7);
  if (BMAP == 3) b = (((b & 63) >> 3) * 2 + (b & 1)) * 8 + (((b < 64 ? 0x7430 : 0x6521) >> (4 * ((b >> 1) & 3))) & 7);
  if (BMAP == 4) b = (((b >> 4) * 2 + (b & 1)) * 8) + ((b >> 1) & 7);
  if (BMAP == 5) b = 127 - b;
  const int r = b >> 3, hg = b & 7;

  if (tid == T_ISSUE) {
    TSM(true, 0);
#pragma unroll
    for (int i = 0; i < 4; i++) mbar_init(bars + 8 * (B_FULL1 + i), 1);
#pragma unroll
    for (int i = 0; i < 3; i++) mbar_init(bars + 8 * (B_KV + i), 1);
    fence_async_smem();
#pragma unroll 1
    for (int kb = 0; kb <= PRE2; kb++) load_stage(sb, kb, b, m);
  } else if (tid >= T_PF && tid < T_PF + 12) {
    tm_prefetch(&m.x + (tid - T_PF));
  } else if (tid == T_INIT) {
#pragma unroll
    for (int i = 0; i < 4; i++) mbar_init(bars + 8 * (B_EMPTY1 + i), 8);
#pragma unroll
    for (int i = 0; i < 8; i++) mbar_init(bars + 8 * (B_FULL2 + i), 1);
#pragma unroll
    for (int i = 0; i < 4; i++) mbar_init(bars + 8 * (B_EMPTY2 + i), 8);
#pragma unroll
    for (int i = 0; i < 4; i++) mbar_init(bars + 8 * (B_U + i), 1);
    mbar_init(bars + 8 * B_HA, 4);
    mbar_init(bars + 8 * B_GATE, 4);
    mbar_init(bars + 8 * B_HB, 1);
    mbar_init(bars + 8 * B_KVD, 4);
    mbar_init(bars + 8 * B_QF, 1);
    mbar_init(bars + 8 * B_ATTN, 8);
    mbar_init(bars + 8 * B_ATT2, 8);
    mbar_init(bars + 8 * B_P1, 8);
    mbar_init(bars + 8 * B_C34, 1);
    mbar_init(bars + 8 * B_YRB, 1);
#pragma unroll
    for (int i = 0; i < 5; i++) mbar_init(bars + 8 * (B_YST + i), 4);
#pragma unroll
    for (int i = 0; i < 5; i++) mbar_init(bars + 8 * (B_US + i), i == 2 ? 20 : i == 1 ? 8 : 1);
    mbar_init(bars + 8 * B_YSIG, 1);
    mbar_init(bars + 8 * B_YFULL, 1);
    mbar_init(bars + 8 * B_EPOCH, 1);
    mbar_init(bars + 8 * B_PREP, 4);
    mbar_init(bars + 8 * B_USIG, 1);
    mbar_init(bars + 8 * B_WST, 1);
#pragma unroll
    for (int i = 3; i < 5; i++) mbar_init(bars + 8 * (B_KV + i), 1);
    mbar_init(bars + 8 * B_E3, 8);
    mbar_init(bars + 8 * B_LAST, 1);
    mbar_init(bars + 8 * B_OSIG, 1);
    mbar_init(bars + 8 * B_WOP, 1);
    fence_async_smem();
  }
  const int warp = __shfl_sync(0xffffffffu, tid >> 5, 0), wg = warp >> 2, w = warp & 3;
  __syncthreads();

  if (wg == 3) {
    asm volatile("setmaxnreg.dec.sync.aligned.u32 56;");
    if (w == 0) {
      if (lane == 0) {
#pragma unroll 1
        for (int kb = 1 + PRE2; kb < 10; kb++) {
          if (kb >= 4) mbar_wait(bars + 8 * (kb == 7 ? B_E3 : B_EMPTY1 + (kb & 3)), (kb >> 3) & 1);
          TSIF(kb >= 4, 44 + kb);
          load_stage(sb, kb, b, m);
          TSIF(kb == 3, 60);
          if (kb == TRIG_KB) mbar_arrive(bars + 8 * B_LAST);
        }
        mbar_wait(bars + 8 * B_WOP, 0);
        mbar_wait(bars + 8 * WL_TRIG, 0);
        mbar_wait(bars + 8 * B_EPOCH, 0);
        flag_wait(g_cnt + C_W + 32 * hg, (lds32(sb + OFF_EPOCH) + 1) * 16);
        TS(30);
#pragma unroll 1
        for (int j = 0; j < 8; j++) {
          if (Q_REG && j == Q_AT) {
            mbar_expect_tx(bars + 8 * B_QF, O_BYTES);
            tma_2d(sb + OFF_QS, &m.qm, 80 * hg, 128 * r, bars + 8 * B_QF);
            tma_2d(sb + OFF_QT, &m.qt, 80 * hg + 64, 128 * r, bars + 8 * B_QF);
          }
          if (j >= 6) mbar_wait(bars + 8 * (B_EMPTY2 + j - 6), 0);
          if (j == 4) mbar_wait(bars + 8 * B_ATTN, 0);
          TSIF(j >= 6, 100 + j);
          if (RF_GATE && j == 6) mbar_wait(bars + 8 * B_YSIG, 0);
          mbar_expect_tx(bars + 8 * (B_FULL2 + j), j == 0 ? WO_BYTES : j == 5 ? O_BYTES + WO_BYTES + 512 : O_BYTES + WO_BYTES);
          bulk_load(sb + off_w(j), g_WO + (hg * 8 + step_src(hg, j)) * 800, WO_BYTES, bars + 8 * (B_FULL2 + j));
        }
        if (!Q_REG) {
          mbar_wait(bars + 8 * (B_EMPTY2 + Q_SLOT), 0);
          mbar_expect_tx(bars + 8 * B_QF, O_BYTES);
          tma_2d(sb + OFF_QS, &m.qm, 80 * hg, 128 * r, bars + 8 * B_QF);
          tma_2d(sb + OFF_QT, &m.qt, 80 * hg + 64, 128 * r, bars + 8 * B_QF);
        }
      }
    } else if (w == 1) {
      unsigned epoch = 0;
      if (lane == 0) {
        epoch = atomicAdd(g_cnt + C_LAUNCH, 1u) / NCTA;
        asm volatile("st.shared.u32 [%0], %1;" ::"r"(sb + OFF_EPOCH), "r"(epoch) : "memory");
        mbar_arrive(bars + 8 * B_EPOCH);
        mbar_wait(bars + 8 * B_KVD, 0);
        mbar_expect_tx(bars + 8 * B_HB, 5 * 4096);
#pragma unroll 1
        for (int c = 0; c < 5; c++) {
          if (c == 3) mbar_wait(bars + 8 * B_S3, 0);
          bulk_load(sb + off_ch(c) + U_BYTES, p.ssm_k + (5 * b + c) * SEQ, 4096, bars + 8 * B_HB);
        }
#pragma unroll
        for (int c = 0; c < 4; c++) mbar_expect_tx(bars + 8 * (B_U + c), c < 3 ? U_BYTES : 2 * U_BYTES);
        const uint4* usrc = g_U + 5 * b * U_PITCH;
        mbar_wait(bars + 8 * B_USIG, 0);
        flag_wait(g_cnt + C_PREP + 32 * (b & 15), (epoch + 1) * NCTA);
        TS(23);
#pragma unroll
        for (int c = 0; c < 5; c++) {
          if (c == 3 && U_TRIM) mbar_wait(bars + 8 * (B_U + 2), 0);
          bulk_load(sb + off_ch(c), usrc + c * U_PITCH, U_BYTES, bars + 8 * (B_U + (c < 3 ? c : 3)));
          TSIF(c == 0 || c == 4, 116 + (c >> 2));
        }
      }
      epoch = __shfl_sync(0xffffffffu, epoch, 0);
      if (lane < 8) {
        const int src = (b & ~7) | step_src(hg, lane);
        mbar_wait(bars + 8 * OP_TRIG, 0);
        TS(20);
        bool seen = false;
#pragma unroll 1
        for (int spins = 0; spins < SPIN_LIMIT; spins++) {
          const bool now = !seen && (int)(flag_read(g_cnt + C_O + 32 * src) - (epoch + 1)) >= 0;
          if (now && lane >= 1 && lane < 4 - Q_REG) bulk_load(sb + off_o(lane), g_O + src * 1280, O_BYTES, bars + 8 * (B_FULL2 + lane));
          seen = seen || now;
          if (__all_sync(0xff, seen)) break;
        }
        TS(21);
        if (lane == 5) bulk_load(sb + OFF_GATE, g_gate + 128 * r, 512, bars + 8 * (B_FULL2 + 5));
#pragma unroll 1
        for (int i = 4 - Q_REG; i < 8; i++) {
          const int j = Q_REG && Q_LATE && i < 6 ? (i == 5 ? 3 : i + 1) : i;
          if (lane == j) {
            mbar_wait(bars + 8 * (j == 3 ? B_QE : j < 6 ? B_C34 : B_EMPTY2 + j - 6), 0);
            if (RF_GATE && j == 6) mbar_wait(bars + 8 * B_YSIG, 0);
            bulk_load(sb + off_o(j), g_O + src * 1280, O_BYTES, bars + 8 * (B_FULL2 + j));
          }
          __syncwarp(0xff);
        }
        TS(22);
      }
    } else if (w == 2) {
      mbar_wait(bars + 8 * B_PREP, 0);
      flag_signal(g_cnt + C_PREP, 16, lane);
      TS(25);
      if (lane == 0) {
        mbar_arrive(bars + 8 * B_USIG);
        mbar_expect_tx(bars + 8 * B_ORB, O_BYTES + 64);
        mbar_wait(bars + 8 * B_GATE, 0);
        bulk_store(g_gate + 16 * b, sb + OFF_GATE + 64 * hg, 64);
        bulk_wait_read<0>();
        bulk_load(sb + OFF_GATE + 64 * hg, g_gate + 16 * b, 64, bars + 8 * B_ORB);
        mbar_wait(bars + 8 * B_ATTN, 0);
        constexpr uint32_t PB = O_BYTES / O_SPLIT;
#pragma unroll
        for (int i = 0; i < O_SPLIT; i++) bulk_store(g_O + b * 1280 + i * (PB / 16), sb + OFF_OA + i * PB, PB);
#pragma unroll
        for (int i = 0; i < O_SPLIT; i++) {
          if (O_SPLIT - 1 - i == 4) bulk_wait_read<4>();
          if (O_SPLIT - 1 - i == 3) bulk_wait_read<3>();
          if (O_SPLIT - 1 - i == 2) bulk_wait_read<2>();
          if (O_SPLIT - 1 - i == 1) bulk_wait_read<1>();
          if (O_SPLIT - 1 - i == 0) bulk_wait_read<0>();
          bulk_load(sb + OFF_OA + i * PB, g_O + b * 1280 + i * (PB / 16), PB, bars + 8 * B_ORB);
        }
        TS(74);
        mbar_wait(bars + 8 * B_ORB, 0);
        flag_bump(g_cnt + C_O + 32 * b);
        TS(26);
        mbar_arrive(bars + 8 * B_OSIG);
      }
    } else {
      if (lane == 0) {
        uint4* dst = g_WO + (hg * 8 + (r >> 1)) * 800 + (r & 1) * 80;
        if (WPF) {
          mbar_wait(bars + 8 * WPF, 0);
          if (WPF_LIN)
            asm volatile("cp.async.bulk.prefetch.L2.global [%0], 6400;" ::"l"(p.wo + b * 3200) : "memory");
          else
            asm volatile("cp.async.bulk.prefetch.tensor.3d.L2.global [%0, {%1, %2, %3}];" ::"l"(&m.wo), "r"(0), "r"(40 * r), "r"(5 * hg) : "memory");
        }
        mbar_wait(bars + 8 * B_P1, 0);
        mbar_wait(bars + 8 * WB_TRIG, 0);
        mbar_expect_tx(bars + 8 * B_WST, WO_BYTES / 2);
        tma_3d(sb + OFF_WS, &m.wo, 0, 40 * r, 5 * hg, bars + 8 * B_WST);
        mbar_wait(bars + 8 * B_WST, 0);
        mbar_wait(bars + 8 * WO_TRIG, 0);
#pragma unroll 1
        for (int n = 0; n < 5; n++)
          asm volatile("cp.async.bulk.global.shared::cta.bulk_group [%0], [%1], 1280;" ::"l"(dst + 160 * n), "r"(sb + OFF_WS + 1280 * n) : "memory");
        if (W_RB) {
          asm volatile("cp.async.bulk.commit_group;\ncp.async.bulk.wait_group.read 0;" ::: "memory");
          mbar_expect_tx(bars + 8 * B_WST, WO_BYTES / 2);
#pragma unroll 1
          for (int n = 0; n < 5; n++) bulk_load(sb + OFF_WS + 1280 * n, dst + 160 * n, 1280, bars + 8 * B_WST);
          mbar_wait(bars + 8 * B_WST, 1);
        } else {
          asm volatile("cp.async.bulk.commit_group;\ncp.async.bulk.wait_group 0;\nfence.proxy.async.global;" ::: "memory");
          if (!(NOMB & 4)) asm volatile("fence.release.gpu;" ::: "memory");
        }
        flag_bump(g_cnt + C_W + 32 * hg);
        mbar_arrive(bars + 8 * B_WOP);
        TS(71);
        mbar_expect_tx(bars + 8 * B_C34, 3 * U_BYTES);
        mbar_expect_tx(bars + 8 * B_YRB, 2 * U_BYTES);
#pragma unroll 1
        for (int c = 0; c < 5; c++) {
          mbar_wait(bars + 8 * (B_YST + c), 0);
          asm volatile("cp.async.bulk.global.shared::cta.bulk_group [%0], [%1], 4096;\ncp.async.bulk.commit_group;\n"
                       "cp.async.bulk.wait_group.read 0;" ::"l"(g_Y + (5 * b + c) * Y_PITCH), "r"(sb + off_ch(c)) : "memory");
          bulk_load(sb + off_ch(c), g_Y + (5 * b + c) * Y_PITCH, U_BYTES, bars + 8 * (c < 3 ? B_C34 : B_YRB));
        }
        TS(75);
        mbar_wait(bars + 8 * B_C34, 0);
        mbar_wait(bars + 8 * B_YRB, 0);
        flag_bump(g_cnt + C_Y + 32 * (b >> 4));
        TS(27);
        mbar_arrive(bars + 8 * B_YSIG);
        mbar_expect_tx(bars + 8 * B_YFULL, 20480);
        flag_wait(g_cnt + C_Y + 32 * hg, (lds32(sb + OFF_EPOCH) + 1) * 16);
        TS(24);
        tma_2d(sb + OFF_YT, &m.y, 128 * r, 80 * hg, bars + 8 * B_YFULL);
        tma_2d(sb + OFF_YT + 10240, &m.y, 128 * r + 64, 80 * hg, bars + 8 * B_YFULL);
      }
    }
  } else {
    asm volatile("setmaxnreg.inc.sync.aligned.u32 152;");
    if (wg < 2) {
      float acc[120];
#pragma unroll
      for (int i = 0; i < 120; i++) acc[i] = 0.f;
      const uint32_t da = desc_lo(sb + wg * 8192, 16), db = desc_lo(sb + ST_W, 8192), dc = desc_lo(sb + ST_WT, 2048);
      if (PW1) pin<120>(acc);
      if (PW1 == 2) mbar_wait(bars + 8 * B_FULL1, 0);
#pragma unroll 1
      for (int kb = 0; kb < 10; kb++) {
        mbar_wait(bars + 8 * (B_FULL1 + (kb & 3)), (kb >> 2) & 1);
        const uint32_t so = (kb & 3) * (STAGE_BYTES >> 4);
        wg_fence();
#pragma unroll
        for (int k = 0; k < 4; k++) {
          WgSST<192>::mma<HI_SW128, HI_SW128>(acc, da + so + 2 * k, db + so + 128 * k, 1);
          WgSST<48>::mma<HI_SW128, HI_SW32>(acc + 96, da + so + 2 * k, dc + so + 32 * k, 1);
        }
        wg_commit();
        wg_wait<1>();
        if (kb > 0 && lane == 0) mbar_arrive(bars + 8 * (kb == 4 ? B_E3 : B_EMPTY1 + ((kb - 1) & 3)));
      }
      mbar_wait(bars + 8 * B_EPOCH, 0);
      const uint32_t tag = lds32(sb + OFF_EPOCH) + 1;
      mbar_wait(bars + 8 * B_S3, 0);
      wg_wait<0>();
      pin<120>(acc);
      if (lane == 0) mbar_arrive(bars + 8 * B_P1);
      TSM(w == 0, 3 + wg);
      attention(acc, sb, b, wg, w, lane, tag, p.zero);
    } else {
      const int tw = tid & 127, chl = 64 * (b & 1) + 8 * w + (lane >> 2);
      uint4* up = g_U + chl * U_PITCH + ((4 * (b >> 1) + (lane & 3)) ^ ((b >> 2) & 1));
      uint2 sw[10];
      uint32_t dv = 0;
      if (lane < 5) dv = __ldg(reinterpret_cast<const unsigned short*>(p.ssm_D) + 5 * b + lane);
#pragma unroll
      for (int i = 0; i < 10; i++) sw[i] = ldg64(reinterpret_cast<const uint2*>(p.shift_k) + chl + 128 * (i >> 1) + 32 * (i & 1));
      uint32_t tab[12];
      uint32_t tt[2];
      fft_tables(tab, tw);
      fft_twiddles(tt, tw);
      uint4 res[10];
#pragma unroll
      for (int i = 0; i < 10; i++) res[i] = make_uint4(0, 0, 0, 0);
#pragma unroll 1
      for (int slab = 0; slab < 5; slab++) {
#pragma unroll
        for (int i = 0; i < 8; i++) res[i] = res[i + 2];
        prep_slab(res + 8, sw, sb, slab, w, lane);
        TSIF(w == 0, 99 + 4 * slab);
#pragma unroll
        for (int i = 0; i < 8; i++) sw[i] = sw[i + 2];
      }
      TSIF(w == 0, 28);
      __syncwarp();
      if (lane == 0) mbar_arrive(bars + 8 * B_KVD + ((res[8].x ^ res[9].x) & p.zero));
      mbar_wait(bars + 8 * B_KVD, 0);
      fft_tables_store(tab, sb, tw);
      mbar_wait(bars + 8 * B_LAST, 0);
#pragma unroll
      for (int i = 0; i < 10; i++) up[(128 * (i >> 1) + 32 * (i & 1)) * U_PITCH] = res[i];
      __syncwarp();
      if (lane == 0) mbar_arrive(bars + 8 * B_PREP);
      TSIF(w == 0 && !U_TMA, 5);
      mbar_wait(bars + 8 * (G_AFTER ? B_USIG : B_LAST), 0);
      prep_gate(p, sb, b, w, lane);
      __syncwarp();
      if (lane == 0) mbar_arrive(bars + 8 * B_GATE);
      TSIF(w == 0, 72);
      mbar_wait(bars + 8 * B_HB, 0);
      TSIF(w == 0, 2);
      const uint32_t ha = sb + U_BYTES + ((tw >> 3) * 16 + 8 + (tw & 7)) * 16;
      uint4 hv[5];
#pragma unroll
      for (int c = 0; c < 5; c++) hv[c] = lds128(ha + off_ch(c));
      __syncwarp();
#pragma unroll
      for (int c = 0; c < 5; c++) sts128((ha ^ 16) + off_ch(c), hv[c].x, hv[c].y, hv[c].z, hv[c].w);
      asm volatile("st.shared.v2.u32 [%0], {%1, %2};" ::"r"(sb + OFF_TT + 8 * tw), "r"(tt[0]), "r"(tt[1]) : "memory");
      if (tw < 5) asm volatile("st.shared.f32 [%0], %1;" ::"r"(sb + OFF_D + 4 * tw), "f"(bf_lo(dv) * 0.125f) : "memory");
      fence_async_smem();
      __syncwarp();
      if (lane == 0) mbar_arrive(bars + 8 * B_HA);
      TSIF(w == 0, 6);
    }

    FftConst fc;
    TSM(w == 0 && wg == 0, 104);
    mbar_wait(bars + 8 * B_HA, 0);
    fft_matrices(fc, sb, w, lane);
    TSM(w == 0 && wg == 0, 105);
    TSM(w == 0 && wg == 2, 124);
    uint32_t tasks = wg == 0 ? TASK0 : wg == 1 ? TASK1 : TASK2, fa[4][4];
    {
      float X[32];
      wg_fence();
      f_step(X, fc, desc_lo(sb + off_ch((tasks & 7) - 1) + U_BYTES, 1024));
      wg_wait<0>();
      pin<32>(X);
      twiddle_fwd(fa, X, fc);
    }
#pragma unroll 1
    for (; tasks; tasks >>= 4) {
      const int c = (tasks & 7) - 1;
      conv_channel(fc, fa, sb, c, ((tasks >> 4) & 7) - 1, wg, w, lane);
      if (lane == 0) mbar_arrive(bars + 8 * (B_YST + c));
      TSM(w == 0, 10 + c);
    }

    if (wg != WO_SKIP) {
      const int wg = (warp >> 2) > WO_SKIP ? (warp >> 2) - 1 : warp >> 2;
      const int g = lane >> 2;
      float acc[40];
#pragma unroll
      for (int i = 0; i < 40; i++) acc[i] = 0.f;
      const uint32_t da = desc_lo(sb + wg * 1024, 2048), db = desc_lo(sb, 2560);
      const int tr = 64 * wg + 16 * w + (lane & 15);
      const uint32_t fm = sb + OFF_QS + tr * 128, fx = (lane >> 4) ^ (tr & 7);
      const uint32_t ft = sb + OFF_QT + tr * 32 + (((lane >> 4) ^ (tr >> 2)) & 1) * 16;
      uint32_t qf[20];
      if (Q_REG) {
        mbar_wait(bars + 8 * B_QF, 0);
#pragma unroll
        for (int j = 0; j < 5; j++) ldsm4(qf + 4 * j, j < 4 ? fm + ((fx ^ (2 * j)) << 4) : ft);
        if (lane == 0) mbar_arrive(bars + 8 * B_QE + ((qf[3] ^ qf[7] ^ qf[11] ^ qf[15] ^ qf[19]) & p.zero));
      }
      mbar_wait(bars + 8 * B_ORB, 0);
      if (PW2) mbar_wait(bars + 8 * B_FULL2, 0);
      mbar_wait(bars + 8 * B_CVD, 0);
      TSM(w == 0, 15 + wg);
#pragma unroll 1
      for (int j = 0; j < 8; j++) {
        mbar_wait(bars + 8 * (B_FULL2 + j), 0);
        TSM(w == 0 && wg == 0, 44 + (j < 4 ? j : j + 6));
        const uint32_t oa = da + (off_o(j) >> 4), ob = db + (off_w(j) >> 4);
        wg_fence();
#pragma unroll
        for (int k = 0; k < 5; k++) WgSST<80>::mma<HI_NONE, HI_SW32>(acc, oa + 256 * k, ob + 32 * k, 1);
        wg_commit();
        wg_wait<1>();
        if (j >= 1 && j <= Q_SLOT + 1 && lane == 0) mbar_arrive(bars + 8 * (B_EMPTY2 + j - 1));
      }
      TSIF(w == 0 && wg == 0, 113);
      const float g0 = __uint_as_float(lds32(sb + OFF_GATE + (64 * wg + 16 * w + g) * 4));
      const float g1 = __uint_as_float(lds32(sb + OFF_GATE + (64 * wg + 16 * w + 8 + g) * 4));
      const uint32_t ga = pack2(g0, g0), gb = pack2(g1, g1);
      const uint32_t na = pack2(1.f - g0, 1.f - g0), nb = pack2(1.f - g1, 1.f - g1);

      if (!Q_REG) {
        mbar_wait(bars + 8 * B_QF, 0);
#pragma unroll
        for (int j = 0; j < 5; j++) ldsm4(qf + 4 * j, j < 4 ? fm + ((fx ^ (2 * j)) << 4) : ft);
      } else {
        mbar_wait(bars + 8 * (B_EMPTY2 + 3), 0);
      }
      TSM(w == 0 && wg == 0, 99);
#pragma unroll
      for (int i = 0; i < 20; i++) {
        qf[i] = bmul((i & 1) ? gb : ga, qf[i]);
        asm volatile("" : "+r"(qf[i]));
      }

      wg_wait<0>();
      pin<40>(acc);
      TSM(w == 0, 17 + wg);
      uint32_t pb[20];
#pragma unroll
      for (int j = 0; j < 10; j++) {
        pb[2 * j] = bmul(na, pack2(acc[4 * j], acc[4 * j + 1]));
        pb[2 * j + 1] = bmul(nb, pack2(acc[4 * j + 2], acc[4 * j + 3]));
        asm volatile("" : "+r"(pb[2 * j]), "+r"(pb[2 * j + 1]));
      }
      const uint32_t ya = sb + OFF_YT + wg * 10240 + ((lane >> 4) * 8 + (lane & 7)) * 128 +
                          (((2 * w + (((lane >> 3) & 1) ^ wg)) ^ (lane & 7)) << 4);
      mbar_wait(bars + 8 * B_YFULL, 0);
      TSM(w == 0 && wg == 0, 19);
#pragma unroll
      for (int j = 0; j < 5; j++) {
        uint32_t y[4];
        ldsm4t(y, ya + 2048 * j);
#pragma unroll
        for (int i = 0; i < 4; i++)
          qf[4 * j + i] = bfma(qf[4 * j + i], y[i], pb[4 * j + i]);
      }
#pragma unroll
      for (int j = 0; j < 5; j++) stsm4(j < 4 ? fm + ((fx ^ (2 * j)) << 4) : ft, qf + 4 * j);
      fence_async_smem();
      __syncwarp();
      if (lane == 0) {
        const int row = 64 * wg + 16 * w;
        asm volatile("cp.async.bulk.tensor.2d.global.shared::cta.bulk_group [%0, {%2, %3}], [%1];"
                     ::"l"(&m.om), "r"(sb + OFF_QS + row * 128), "r"(80 * hg), "r"(128 * r + row) : "memory");
        asm volatile("cp.async.bulk.tensor.2d.global.shared::cta.bulk_group [%0, {%2, %3}], [%1];"
                     ::"l"(&m.ot), "r"(sb + OFF_QT + row * 32), "r"(80 * hg + 64), "r"(128 * r + row) : "memory");
        asm volatile("cp.async.bulk.commit_group;\ncp.async.bulk.wait_group.read 0;" ::: "memory");
      }
      TSM(w == 0 || w == 3, 40 + 2 * wg + (w & 1));
      if (ENDBAR) asm volatile("bar.sync 15, 256;" ::: "memory");
    }
  }
}

typedef CUresult (*EncodeFn)(CUtensorMap*, CUtensorMapDataType, cuuint32_t, void*, const cuuint64_t*, const cuuint64_t*,
                             const cuuint32_t*, const cuuint32_t*, CUtensorMapInterleave, CUtensorMapSwizzle,
                             CUtensorMapL2promotion, CUtensorMapFloatOOBfill);

void encode(EncodeFn fn, CUtensorMap* tm, const void* base, int rank, const cuuint64_t* dims, const cuuint64_t* strides,
            const cuuint32_t* box, CUtensorMapSwizzle swz) {
  const cuuint32_t ones[3] = {1, 1, 1};
  fn(tm, CU_TENSOR_MAP_DATA_TYPE_BFLOAT16, rank, const_cast<void*>(base), dims, strides, box, ones,
     CU_TENSOR_MAP_INTERLEAVE_NONE, swz, CU_TENSOR_MAP_L2_PROMOTION_L2_128B, CU_TENSOR_MAP_FLOAT_OOB_FILL_NONE);
}

}

extern "C" void kernel_launch(void* const* d_in, const int* in_sizes, int n_in, void* d_out, int out_size) {
  (void)in_sizes; (void)n_in; (void)out_size;
  Params p;
  p.q = (const __nv_bfloat16*)d_in[0];
  p.k = (const __nv_bfloat16*)d_in[1];
  p.v = (const __nv_bfloat16*)d_in[2];
  p.shift_k = (const __nv_bfloat16*)d_in[3];
  p.ssm_k = (const __nv_bfloat16*)d_in[4];
  p.ssm_D = (const __nv_bfloat16*)d_in[5];
  p.wqkv = (const __nv_bfloat16*)d_in[7];
  p.wo = (const __nv_bfloat16*)d_in[8];
  p.gate_w = (const __nv_bfloat16*)d_in[9];
  p.out = (__nv_bfloat16*)d_out;
  p.zero = 0;

  static EncodeFn fn = nullptr;
  static void *yaddr = nullptr, *uaddr = nullptr;
  if (!fn) {
    cudaDriverEntryPointQueryResult qr;
    void* f = nullptr;
    cudaGetDriverEntryPoint("cuTensorMapEncodeTiled", &f, cudaEnableDefault, &qr);
    fn = (EncodeFn)f;
    cudaGetSymbolAddress(&yaddr, g_Y);
    cudaGetSymbolAddress(&uaddr, g_U);
    cudaFuncSetAttribute(fused_kernel, cudaFuncAttributeMaxDynamicSharedMemorySize, SMEM_BYTES);
  }
  Maps m;
  {
    const cuuint64_t dims[3] = {640, 1024, 2}, st[2] = {2560, 1280};
    const cuuint32_t box[3] = {64, 64, 2};
    encode(fn, &m.x, p.q, 3, dims, st, box, CU_TENSOR_MAP_SWIZZLE_128B);
  }
  {
    const cuuint64_t dims[3] = {640, 640, 3}, st[2] = {3840, 1280};
    const cuuint32_t box[3] = {64, 64, 3}, boxt[3] = {16, 64, 3};
    encode(fn, &m.wm, p.wqkv, 3, dims, st, box, CU_TENSOR_MAP_SWIZZLE_128B);
    encode(fn, &m.wt, p.wqkv, 3, dims, st, boxt, CU_TENSOR_MAP_SWIZZLE_32B);
  }
  {
    const cuuint64_t dims[3] = {64, 2048, 10}, st[2] = {1280, 128};
    const cuuint32_t boxk[3] = {64, 35, 1}, boxv[3] = {64, 32, 1};
    encode(fn, &m.k, p.k, 3, dims, st, boxk, CU_TENSOR_MAP_SWIZZLE_128B);
    encode(fn, &m.v, p.v, 3, dims, st, boxv, CU_TENSOR_MAP_SWIZZLE_128B);
  }
  {
    const cuuint64_t dims[3] = {16, 640, 40}, st[2] = {1280, 32};
    const cuuint32_t box[3] = {16, 40, 5};
    encode(fn, &m.wo, p.wo, 3, dims, st, box, CU_TENSOR_MAP_SWIZZLE_32B);
  }
  {
    const cuuint64_t dims[2] = {2048, 640}, st[1] = {Y_PITCH * 16};
    const cuuint32_t box[2] = {64, 80};
    encode(fn, &m.y, yaddr, 2, dims, st, box, CU_TENSOR_MAP_SWIZZLE_128B);
    const cuuint64_t stu[1] = {U_PITCH * 16};
    const cuuint32_t boxu[2] = {32, 64};
    encode(fn, &m.u, uaddr, 2, dims, stu, boxu, CU_TENSOR_MAP_SWIZZLE_NONE);
  }
  {
    const cuuint64_t dims[2] = {640, 2048}, st[1] = {1280};
    const cuuint32_t bqm[2] = {64, 128}, bqt[2] = {16, 128}, bom[2] = {64, 16}, bot[2] = {16, 16};
    encode(fn, &m.qm, p.q, 2, dims, st, bqm, CU_TENSOR_MAP_SWIZZLE_128B);
    encode(fn, &m.qt, p.q, 2, dims, st, bqt, CU_TENSOR_MAP_SWIZZLE_32B);
    encode(fn, &m.om, p.out, 2, dims, st, bom, CU_TENSOR_MAP_SWIZZLE_128B);
    encode(fn, &m.ot, p.out, 2, dims, st, bot, CU_TENSOR_MAP_SWIZZLE_32B);
  }
  fused_kernel<<<NCTA, NTHR, SMEM_BYTES>>>(m, p);
}
```

```cpp
#include <cuda.h>
#include <cuda_bf16.h>
#include <cuda_runtime.h>
#include <stdint.h>

namespace {

constexpr int SEQ = 2048, DIM = 640, NCTA = 128, NTHR = 512;

#define TRIG_KB 9
#define KV_KB 2
#define DEV_EXIT 0
#define ATT_GATE 0
#define G_AFTER 0
#define FENCE_LO 0
#define FENCE_HI 0
#define PW1 2
#define PW2 1
#define ENDBAR 0
#define PAD_KB 0
#define Y_ALIAS 1
#define NOMB 0
#define SRC_ROT 0
#define WAIT_NS 0
#define WB_TRIG B_USIG
#define G_POS 0
#define TAILF 1
#define T_ISSUE 384
#define T_PF 416
#define T_INIT 448
#define ATT_MERGE 0
#define BMAP 1
#define PRE2 1
#define KV_MIX 0
#define O_DEFER 0
#define TASK0 0x3
#define TASK1 0x52
#define TASK2 0x41
#define HALO_FIRST 1
#define PREV_EARLY 0
#define Y_RB 2
#define O_RB 2
#define O_EAGER 1
#define OP_TRIG B_ATTN
#define U_TRIM 1
#define Q_SLOT 3
#define G_TMA 1
#define W_RB 1
#define WPF B_S3
#define WPF_LIN 1
#define O_SPLIT 1
#define WO_SKIP 1
#define Q_REG 2
#define Q_AT 0
#define ACQ 0
#define U_TMA 0
#define U_GATE 0
#define RF_GATE 0
#define WO_TRIG B_WST
#define WL_TRIG B_WOP
#define WO_GATE 4

constexpr uint32_t STAGE_BYTES = 47104, ST_W = 16384, ST_WT = 40960;
constexpr uint32_t O_BYTES = 20480, WO_BYTES = 12800;
constexpr uint32_t OFF_OA = 0;
constexpr uint32_t OFF_QS = Q_SLOT * O_BYTES, OFF_QT = OFF_QS + 16384;
constexpr uint32_t OFF_WC = 81920;
constexpr uint32_t OFF_WA = 94720;
constexpr uint32_t OFF_GATE = 145920;
constexpr uint32_t OFF_TT = 146432;
constexpr uint32_t OFF_KVX = 148480;
constexpr uint32_t OFF_CH3 = 163840;
constexpr uint32_t CH_BYTES = 12288, U_BYTES = 4096;
constexpr uint32_t OFF_FT = 225280, OFF_GT = 229376;
constexpr uint32_t OFF_CH0 = 188416;
constexpr uint32_t OFF_KVS = OFF_CH0, KVS_V = 4480, KVS_BYTES = 8576;
constexpr uint32_t OFF_WS = OFF_WA;
__device__ __forceinline__ uint32_t off_us(int s) { return OFF_CH0 + 4096 * ((0x65320 >> (4 * s)) & 7); }
constexpr uint32_t OFF_YT = 163840;
constexpr uint32_t OFF_BAR = 231936;
constexpr uint32_t SMEM_BYTES = OFF_BAR + 512;

enum : uint32_t {
  B_FULL1 = 0, B_EMPTY1 = 4, B_S3 = 7, B_FULL2 = 52, B_EMPTY2 = 13, B_U = 8, B_GATE = 12, B_HA = 19, B_HB = 20,
  B_ATTN = 21, B_C34 = 22, B_YRB = 23, B_YFULL = 24, B_EPOCH = 25, B_PREP = 26, B_P1 = 27, B_LAST = 28,
  B_E3 = 29, B_OSIG = 30, B_WOP = 31, B_USIG = 32, B_WST = 33, B_KV = 34, B_KVD = 39, B_QF = 17, B_ATT2 = 18, B_YST = 40,
  B_ORB = 45, B_QE = 46, B_CVD = 33 + 14, B_US = 45, B_YSIG = 50
};
constexpr uint32_t OFF_EPOCH = OFF_BAR + 8 * 51, OFF_D = OFF_BAR + 8 * 60;
__device__ __forceinline__ uint32_t off_o(int j) {
  if (Q_REG == 2) return j < 3 ? OFF_OA + j * O_BYTES : j < 5 ? OFF_CH0 + (j - 3) * O_BYTES : OFF_OA + (j == 5 ? 3 : j - 6) * O_BYTES;
  return j < 4 ? OFF_OA + j * O_BYTES : j < 6 ? OFF_CH0 + (j - 4) * O_BYTES : OFF_OA + (j - 6) * O_BYTES; }
__device__ __forceinline__ uint32_t off_w(int j) { return j < 4 ? OFF_WA + j * WO_BYTES : j == 4 ? OFF_KVX : j == 5 ? OFF_WC : OFF_WA + (j - 6) * WO_BYTES; }
__device__ __forceinline__ int step_src(int hg, int j) {
  if (SRC_ROT == 2) {
    const int pos = (0x37621540 >> (4 * hg)) & 7;
    return j == 0 ? hg : (0x65217430 >> (4 * (j <= pos ? j - 1 : j))) & 7;
  }
  return SRC_ROT ? (hg + j) & 7 : j == 0 ? hg : j <= hg ? j - 1 : j;
}
__device__ __forceinline__ bool tail_first(int hg) { return TAILF && (hg & 3) == 3; }
__device__ __forceinline__ uint32_t off_ch(int c) { return (c < 3 ? OFF_CH0 : OFF_CH3 - 3 * CH_BYTES) + c * CH_BYTES; }

#define U_PITCH 264
__device__ __align__(1024) uint4 g_U[DIM * U_PITCH];
__device__ uint4 g_O[NCTA * 1280];
#define g_Y g_U
constexpr int Y_PITCH = U_PITCH;
__device__ uint4 g_WO[64 * 800];
__device__ uint4 g_halo[NCTA * 2 * 7 * 32];
__device__ __align__(128) float g_gate[SEQ + PAD_KB * 256];
__device__ unsigned g_cnt[32 * (1 + 2 * 16 + 8 + NCTA)];
constexpr int C_LAUNCH = 0, C_PREP = 32, C_Y = 32 * 17, C_W = 32 * 33, C_O = 32 * 41;

#define TSM(cond, slot) do { } while (0)
#define TSIF(cond, slot) do { if (__LINE__ >= FENCE_LO && __LINE__ < FENCE_HI) sched_fence(); } while (0)
__device__ __forceinline__ void sched_fence() {
  asm volatile("{\n.reg .pred p;\n.reg .u32 c;\nmov.u32 c, %%clock;\nsetp.eq.u32 p, c, 0;\n@p st.shared.u32 [%0], c;\n}"
               ::"r"(1024 + OFF_EPOCH + 4) : "memory");
}
#define TS(slot) TSIF(true, slot)

struct Params {
  const __nv_bfloat16 *q, *k, *v, *shift_k, *ssm_k, *ssm_D, *wqkv, *wo, *gate_w;
  __nv_bfloat16* out;
  uint32_t zero;
};

#define POLL_NS 0
constexpr int SPIN_LIMIT = 1 << 17;

__device__ __forceinline__ void mbar_init(uint32_t bar, uint32_t count) {
  asm volatile("mbarrier.init.shared::cta.b64 [%0], %1;" ::"r"(bar), "r"(count) : "memory");
}
__device__ __forceinline__ void mbar_expect_tx(uint32_t bar, uint32_t bytes) {
  asm volatile("mbarrier.arrive.expect_tx.shared::cta.b64 _, [%0], %1;" ::"r"(bar), "r"(bytes) : "memory");
}
__device__ __forceinline__ void mbar_arrive(uint32_t bar) {
  asm volatile("mbarrier.arrive.shared::cta.b64 _, [%0];" ::"r"(bar) : "memory");
}
__device__ __forceinline__ void mbar_wait(uint32_t bar, uint32_t parity) {
  uint32_t ok;
  int spins = 0;
  do {
    if (WAIT_NS)
      asm volatile("{\n.reg .pred p;\nmbarrier.try_wait.parity.shared::cta.b64 p, [%1], %2, %3;\nselp.b32 %0, 1, 0, p;\n}"
                   : "=r"(ok) : "r"(bar), "r"(parity), "r"(WAIT_NS) : "memory");
    else
      asm volatile("{\n.reg .pred p;\nmbarrier.try_wait.parity.shared::cta.b64 p, [%1], %2;\nselp.b32 %0, 1, 0, p;\n}"
                   : "=r"(ok) : "r"(bar), "r"(parity) : "memory");
    if (++spins > SPIN_LIMIT) break;
  } while (!ok);
}
__device__ __forceinline__ unsigned flag_read(const unsigned* p) {
  unsigned v;
  asm volatile("ld.relaxed.gpu.global.u32 %0, [%1];" : "=r"(v) : "l"(p) : "memory");
  return v;
}
__device__ __forceinline__ void flag_poll(const unsigned* p, unsigned target) {
  unsigned v;
  int spins = 0;
  do {
    if (POLL_NS && spins) __nanosleep(POLL_NS);
    asm volatile("ld.relaxed.gpu.global.u32 %0, [%1];" : "=r"(v) : "l"(p) : "memory");
    if (++spins > SPIN_LIMIT) break;
  } while ((int)(v - target) < 0);
}
__device__ __forceinline__ void flag_wait(const unsigned* p, unsigned target) {
  flag_poll(p, target);
  if (ACQ) asm volatile("fence.acquire.gpu;\nfence.proxy.async.global;" ::: "memory");
}
__device__ __forceinline__ void flag_signal(unsigned* p, int n, int lane) {
  if (lane == 0) asm volatile("fence.release.gpu;" ::: "memory");
  __syncwarp();
  if (lane < n) asm volatile("red.relaxed.gpu.global.add.u32 [%0], 1;" ::"l"(p + 32 * lane) : "memory");
}
__device__ __forceinline__ void flag_bump(unsigned* p) {
  asm volatile("red.relaxed.gpu.global.add.u32 [%0], 1;" ::"l"(p) : "memory");
}
__device__ __forceinline__ void fence_async_smem() { asm volatile("fence.proxy.async.shared::cta;" ::: "memory"); }
__device__ __forceinline__ void wg_sync(int id) { asm volatile("bar.sync %0, 128;" ::"r"(id) : "memory"); }

__device__ __forceinline__ void tma_2d(uint32_t dst, const CUtensorMap* tm, int c0, int c1, uint32_t bar) {
  asm volatile("cp.async.bulk.tensor.2d.shared::cluster.global.mbarrier::complete_tx::bytes [%0], [%1, {%3, %4}], [%2];"
               ::"r"(dst), "l"(tm), "r"(bar), "r"(c0), "r"(c1) : "memory");
}
__device__ __forceinline__ void tma_3d(uint32_t dst, const CUtensorMap* tm, int c0, int c1, int c2, uint32_t bar) {
  asm volatile("cp.async.bulk.tensor.3d.shared::cluster.global.mbarrier::complete_tx::bytes [%0], [%1, {%3, %4, %5}], [%2];"
               ::"r"(dst), "l"(tm), "r"(bar), "r"(c0), "r"(c1), "r"(c2) : "memory");
}
__device__ __forceinline__ void bulk_load(uint32_t dst, const void* src, uint32_t bytes, uint32_t bar) {
  asm volatile("cp.async.bulk.shared::cluster.global.mbarrier::complete_tx::bytes [%0], [%1], %2, [%3];"
               ::"r"(dst), "l"(src), "r"(bytes), "r"(bar) : "memory");
}
__device__ __forceinline__ void bulk_store(void* dst, uint32_t src, uint32_t bytes) {
  asm volatile("cp.async.bulk.global.shared::cta.bulk_group [%0], [%1], %2;\ncp.async.bulk.commit_group;"
               ::"l"(dst), "r"(src), "r"(bytes) : "memory");
}
template <int N> __device__ __forceinline__ void bulk_wait_read() { asm volatile("cp.async.bulk.wait_group.read %0;" ::"n"(N) : "memory"); }
__device__ __forceinline__ void tm_prefetch(const CUtensorMap* tm) {
  asm volatile("prefetch.tensormap [%0];" ::"l"(tm) : "memory");
}

__device__ __forceinline__ void wg_fence() { asm volatile("wgmma.fence.sync.aligned;" ::: "memory"); }
__device__ __forceinline__ void wg_commit() { asm volatile("wgmma.commit_group.sync.aligned;" ::: "memory"); }
template <int N> __device__ __forceinline__ void wg_wait() { asm volatile("wgmma.wait_group.sync.aligned %0;" ::"n"(N) : "memory"); }
__device__ __forceinline__ uint32_t desc_lo(uint32_t addr, uint32_t lbo) { return ((addr & 0x3FFFF) >> 4) | ((lbo >> 4) << 16); }
constexpr uint32_t desc_hi(uint32_t sbo, uint32_t swz) { return (sbo >> 4) | (swz << 30); }
constexpr uint32_t HI_SW128 = desc_hi(1024, 1), HI_SW64 = desc_hi(512, 2), HI_SW32 = desc_hi(256, 3), HI_NONE = desc_hi(128, 0);
template <int N> __device__ __forceinline__ void pin(float* d) {
#pragma unroll
  for (int i = 0; i < N; i++) asm volatile("" : "+f"(d[i])::"memory");
}

__device__ __forceinline__ uint32_t lds32(uint32_t a) {
  uint32_t v;
  asm volatile("ld.volatile.shared.u32 %0, [%1];" : "=r"(v) : "r"(a) : "memory");
  return v;
}
__device__ __forceinline__ uint4 ldg128(const void* a) {
  uint4 v;
  asm volatile("ld.global.nc.v4.u32 {%0, %1, %2, %3}, [%4];" : "=r"(v.x), "=r"(v.y), "=r"(v.z), "=r"(v.w) : "l"(a) : "memory");
  return v;
}
__device__ __forceinline__ uint2 ldg64(const void* a) {
  uint2 v;
  asm volatile("ld.global.nc.v2.u32 {%0, %1}, [%2];" : "=r"(v.x), "=r"(v.y) : "l"(a) : "memory");
  return v;
}
__device__ __forceinline__ void ldsm4(uint32_t* r, uint32_t a) {
  asm volatile("ldmatrix.sync.aligned.m8n8.x4.shared.b16 {%0, %1, %2, %3}, [%4];"
               : "=r"(r[0]), "=r"(r[1]), "=r"(r[2]), "=r"(r[3]) : "r"(a) : "memory");
}
__device__ __forceinline__ void ldsm4t(uint32_t* r, uint32_t a) {
  asm volatile("ldmatrix.sync.aligned.m8n8.x4.trans.shared.b16 {%0, %1, %2, %3}, [%4];"
               : "=r"(r[0]), "=r"(r[1]), "=r"(r[2]), "=r"(r[3]) : "r"(a) : "memory");
}
__device__ __forceinline__ uint2 lds64(uint32_t a) {
  uint2 v;
  asm volatile("ld.shared.v2.u32 {%0, %1}, [%2];" : "=r"(v.x), "=r"(v.y) : "r"(a) : "memory");
  return v;
}
__device__ __forceinline__ uint4 lds128(uint32_t a) {
  uint4 v;
  asm volatile("ld.shared.v4.u32 {%0, %1, %2, %3}, [%4];" : "=r"(v.x), "=r"(v.y), "=r"(v.z), "=r"(v.w) : "r"(a) : "memory");
  return v;
}
__device__ __forceinline__ void sts128(uint32_t a, uint32_t x, uint32_t y, uint32_t z, uint32_t w) {
  asm volatile("st.shared.v4.u32 [%0], {%1, %2, %3, %4};" ::"r"(a), "r"(x), "r"(y), "r"(z), "r"(w) : "memory");
}
__device__ __forceinline__ void stsm4(uint32_t a, const uint32_t* r) {
  asm volatile("stmatrix.sync.aligned.m8n8.x4.shared.b16 [%0], {%1, %2, %3, %4};" ::"r"(a), "r"(r[0]), "r"(r[1]), "r"(r[2]), "r"(r[3]) : "memory");
}
__device__ __forceinline__ void stsm4t(uint32_t a, const uint32_t* r) {
  asm volatile("stmatrix.sync.aligned.m8n8.x4.trans.shared.b16 [%0], {%1, %2, %3, %4};" ::"r"(a), "r"(r[0]), "r"(r[1]), "r"(r[2]), "r"(r[3]) : "memory");
}
__device__ __forceinline__ uint32_t pack2(float lo, float hi) {
  uint32_t r;
  asm("cvt.rn.bf16x2.f32 %0, %1, %2;" : "=r"(r) : "f"(hi), "f"(lo));
  return r;
}
__device__ __forceinline__ uint32_t movm(uint32_t a) {
  uint32_t d;
  asm volatile("movmatrix.sync.aligned.m8n8.trans.b16 %0, %1;" : "=r"(d) : "r"(a));
  return d;
}
__device__ __forceinline__ uint32_t bmul(uint32_t a, uint32_t b) {
  uint32_t d;
  asm("mul.rn.bf16x2 %0, %1, %2;" : "=r"(d) : "r"(a), "r"(b));
  return d;
}
__device__ __forceinline__ uint32_t badd(uint32_t a, uint32_t b) {
  uint32_t d;
  asm("add.rn.bf16x2 %0, %1, %2;" : "=r"(d) : "r"(a), "r"(b));
  return d;
}
__device__ __forceinline__ uint32_t bfma(uint32_t a, uint32_t b, uint32_t c) {
  uint32_t d;
  asm("fma.rn.bf16x2 %0, %1, %2, %3;" : "=r"(d) : "r"(a), "r"(b), "r"(c));
  return d;
}
__device__ __forceinline__ float bf_lo(uint32_t x) { return __uint_as_float(x << 16); }
__device__ __forceinline__ float bf_hi(uint32_t x) { return __uint_as_float(x & 0xFFFF0000u); }
__device__ __forceinline__ float ex2(float x) {
  float y;
  asm("ex2.approx.ftz.f32 %0, %1;" : "=f"(y) : "f"(x));
  return y;
}
__device__ __forceinline__ float rcp(float x) {
  float y;
  asm("rcp.approx.ftz.f32 %0, %1;" : "=f"(y) : "f"(x));
  return y;
}
__device__ __forceinline__ void mma16816(float* d, uint32_t a0, uint32_t a1, uint32_t a2, uint32_t a3, uint32_t b0, uint32_t b1) {
  asm volatile("mma.sync.aligned.m16n8k16.row.col.f32.bf16.bf16.f32 {%0, %1, %2, %3}, {%4, %5, %6, %7}, {%8, %9}, {%0, %1, %2, %3};"
               : "+f"(d[0]), "+f"(d[1]), "+f"(d[2]), "+f"(d[3])
               : "r"(a0), "r"(a1), "r"(a2), "r"(a3), "r"(b0), "r"(b1));
}
__device__ __forceinline__ void mma1688(float* d, uint32_t a0, uint32_t a1, uint32_t b0) {
  asm volatile("mma.sync.aligned.m16n8k8.row.col.f32.bf16.bf16.f32 {%0, %1, %2, %3}, {%4, %5}, {%6}, {%0, %1, %2, %3};"
               : "+f"(d[0]), "+f"(d[1]), "+f"(d[2]), "+f"(d[3])
               : "r"(a0), "r"(a1), "r"(b0));
}

template <int N> struct WgRS;
template <int N> struct WgSST;
template <> struct WgRS<32> {
  template <uint32_t HB>
  static __device__ __forceinline__ void mma(float* d, const uint32_t* a, uint32_t db) {
    asm volatile("{\n.reg .pred p;\n.reg .b64 db;\nsetp.ne.b32 p, %22, 0;\n"
      "mov.b64 db, {%20, %21};\n"
      "wgmma.mma_async.sync.aligned.m64n32k16.f32.bf16.bf16 {"
      "%0, %1, %2, %3, %4, %5, %6, %7, %8, %9, %10, %11, %12, %13, %14, %15"
      "}, {%16, %17, %18, %19}, db, p, 1, 1, 1;\n}\n"
      : "+f"(d[0]), "+f"(d[1]), "+f"(d[2]), "+f"(d[3]), "+f"(d[4]), "+f"(d[5]), "+f"(d[6]), "+f"(d[7]),
        "+f"(d[8]), "+f"(d[9]), "+f"(d[10]), "+f"(d[11]), "+f"(d[12]), "+f"(d[13]), "+f"(d[14]), "+f"(d[15])
      : "r"(a[0]), "r"(a[1]), "r"(a[2]), "r"(a[3]), "r"(db), "n"(HB), "n"(1));
  }
  template <uint32_t HB>
  static __device__ __forceinline__ void set(float* d, const uint32_t* a, uint32_t db) {
    asm volatile("{\n.reg .pred p;\n.reg .b64 db;\nsetp.ne.b32 p, %22, 0;\n"
      "mov.b64 db, {%20, %21};\n"
      "wgmma.mma_async.sync.aligned.m64n32k16.f32.bf16.bf16 {"
      "%0, %1, %2, %3, %4, %5, %6, %7, %8, %9, %10, %11, %12, %13, %14, %15"
      "}, {%16, %17, %18, %19}, db, p, 1, 1, 1;\n}\n"
      : "=f"(d[0]), "=f"(d[1]), "=f"(d[2]), "=f"(d[3]), "=f"(d[4]), "=f"(d[5]), "=f"(d[6]), "=f"(d[7]),
        "=f"(d[8]), "=f"(d[9]), "=f"(d[10]), "=f"(d[11]), "=f"(d[12]), "=f"(d[13]), "=f"(d[14]), "=f"(d[15])
      : "r"(a[0]), "r"(a[1]), "r"(a[2]), "r"(a[3]), "r"(db), "n"(HB), "n"(0));
  }
};
template <> struct WgRS<64> {
  template <uint32_t HB>
  static __device__ __forceinline__ void mma(float* d, const uint32_t* a, uint32_t db) {
    asm volatile("{\n.reg .pred p;\n.reg .b64 db;\nsetp.ne.b32 p, %38, 0;\n"
      "mov.b64 db, {%36, %37};\n"
      "wgmma.mma_async.sync.aligned.m64n64k16.f32.bf16.bf16 {"
      "%0, %1, %2, %3, %4, %5, %6, %7, %8, %9, %10, %11, %12, %13, %14, %15, "
      "%16, %17, %18, %19, %20, %21, %22, %23, %24, %25, %26, %27, %28, %29, %30, %31"
      "}, {%32, %33, %34, %35}, db, p, 1, 1, 1;\n}\n"
      : "+f"(d[0]), "+f"(d[1]), "+f"(d[2]), "+f"(d[3]), "+f"(d[4]), "+f"(d[5]), "+f"(d[6]), "+f"(d[7]),
        "+f"(d[8]), "+f"(d[9]), "+f"(d[10]), "+f"(d[11]), "+f"(d[12]), "+f"(d[13]), "+f"(d[14]), "+f"(d[15]),
        "+f"(d[16]), "+f"(d[17]), "+f"(d[18]), "+f"(d[19]), "+f"(d[20]), "+f"(d[21]), "+f"(d[22]), "+f"(d[23]),
        "+f"(d[24]), "+f"(d[25]), "+f"(d[26]), "+f"(d[27]), "+f"(d[28]), "+f"(d[29]), "+f"(d[30]), "+f"(d[31])
      : "r"(a[0]), "r"(a[1]), "r"(a[2]), "r"(a[3]), "r"(db), "n"(HB), "n"(1));
  }
  template <uint32_t HB>
  static __device__ __forceinline__ void set(float* d, const uint32_t* a, uint32_t db) {
    asm volatile("{\n.reg .pred p;\n.reg .b64 db;\nsetp.ne.b32 p, %38, 0;\n"
      "mov.b64 db, {%36, %37};\n"
      "wgmma.mma_async.sync.aligned.m64n64k16.f32.bf16.bf16 {"
      "%0, %1, %2, %3, %4, %5, %6, %7, %8, %9, %10, %11, %12, %13, %14, %15, "
      "%16, %17, %18, %19, %20, %21, %22, %23, %24, %25, %26, %27, %28, %29, %30, %31"
      "}, {%32, %33, %34, %35}, db, p, 1, 1, 1;\n}\n"
      : "=f"(d[0]), "=f"(d[1]), "=f"(d[2]), "=f"(d[3]), "=f"(d[4]), "=f"(d[5]), "=f"(d[6]), "=f"(d[7]),
        "=f"(d[8]), "=f"(d[9]), "=f"(d[10]), "=f"(d[11]), "=f"(d[12]), "=f"(d[13]), "=f"(d[14]), "=f"(d[15]),
        "=f"(d[16]), "=f"(d[17]), "=f"(d[18]), "=f"(d[19]), "=f"(d[20]), "=f"(d[21]), "=f"(d[22]), "=f"(d[23]),
        "=f"(d[24]), "=f"(d[25]), "=f"(d[26]), "=f"(d[27]), "=f"(d[28]), "=f"(d[29]), "=f"(d[30]), "=f"(d[31])
      : "r"(a[0]), "r"(a[1]), "r"(a[2]), "r"(a[3]), "r"(db), "n"(HB), "n"(0));
  }
};
template <> struct WgSST<48> {
  template <uint32_t HA, uint32_t HB>
  static __device__ __forceinline__ void mma(float* d, uint32_t da, uint32_t db, int sc) {
    asm volatile("{\n.reg .pred p;\n.reg .b64 da, db;\nsetp.ne.b32 p, %28, 0;\n"
      "mov.b64 da, {%24, %25};\nmov.b64 db, {%26, %27};\n"
      "wgmma.mma_async.sync.aligned.m64n48k16.f32.bf16.bf16 {"
      "%0, %1, %2, %3, %4, %5, %6, %7, %8, %9, %10, %11, %12, %13, %14, %15, "
      "%16, %17, %18, %19, %20, %21, %22, %23"
      "}, da, db, p, 1, 1, 0, 1;\n}\n"
      : "+f"(d[0]), "+f"(d[1]), "+f"(d[2]), "+f"(d[3]), "+f"(d[4]), "+f"(d[5]), "+f"(d[6]), "+f"(d[7]),
        "+f"(d[8]), "+f"(d[9]), "+f"(d[10]), "+f"(d[11]), "+f"(d[12]), "+f"(d[13]), "+f"(d[14]), "+f"(d[15]),
        "+f"(d[16]), "+f"(d[17]), "+f"(d[18]), "+f"(d[19]), "+f"(d[20]), "+f"(d[21]), "+f"(d[22]), "+f"(d[23])
      : "r"(da), "n"(HA), "r"(db), "n"(HB), "r"(sc));
  }
};
template <> struct WgSST<80> {
  template <uint32_t HA, uint32_t HB>
  static __device__ __forceinline__ void mma(float* d, uint32_t da, uint32_t db, int sc) {
    asm volatile("{\n.reg .pred p;\n.reg .b64 da, db;\nsetp.ne.b32 p, %44, 0;\n"
      "mov.b64 da, {%40, %41};\nmov.b64 db, {%42, %43};\n"
      "wgmma.mma_async.sync.aligned.m64n80k16.f32.bf16.bf16 {"
      "%0, %1, %2, %3, %4, %5, %6, %7, %8, %9, %10, %11, %12, %13, %14, %15, "
      "%16, %17, %18, %19, %20, %21, %22, %23, %24, %25, %26, %27, %28, %29, %30, %31, "
      "%32, %33, %34, %35, %36, %37, %38, %39"
      "}, da, db, p, 1, 1, 0, 1;\n}\n"
      : "+f"(d[0]), "+f"(d[1]), "+f"(d[2]), "+f"(d[3]), "+f"(d[4]), "+f"(d[5]), "+f"(d[6]), "+f"(d[7]),
        "+f"(d[8]), "+f"(d[9]), "+f"(d[10]), "+f"(d[11]), "+f"(d[12]), "+f"(d[13]), "+f"(d[14]), "+f"(d[15]),
        "+f"(d[16]), "+f"(d[17]), "+f"(d[18]), "+f"(d[19]), "+f"(d[20]), "+f"(d[21]), "+f"(d[22]), "+f"(d[23]),
        "+f"(d[24]), "+f"(d[25]), "+f"(d[26]), "+f"(d[27]), "+f"(d[28]), "+f"(d[29]), "+f"(d[30]), "+f"(d[31]),
        "+f"(d[32]), "+f"(d[33]), "+f"(d[34]), "+f"(d[35]), "+f"(d[36]), "+f"(d[37]), "+f"(d[38]), "+f"(d[39])
      : "r"(da), "n"(HA), "r"(db), "n"(HB), "r"(sc));
  }
};
template <> struct WgSST<192> {
  template <uint32_t HA, uint32_t HB>
  static __device__ __forceinline__ void mma(float* d, uint32_t da, uint32_t db, int sc) {
    asm volatile("{\n.reg .pred p;\n.reg .b64 da, db;\nsetp.ne.b32 p, %100, 0;\n"
      "mov.b64 da, {%96, %97};\nmov.b64 db, {%98, %99};\n"
      "wgmma.mma_async.sync.aligned.m64n192k16.f32.bf16.bf16 {"
      "%0, %1, %2, %3, %4, %5, %6, %7, %8, %9, %10, %11, %12, %13, %14, %15, "
      "%16, %17, %18, %19, %20, %21, %22, %23, %24, %25, %26, %27, %28, %29, %30, %31, "
      "%32, %33, %34, %35, %36, %37, %38, %39, %40, %41, %42, %43, %44, %45, %46, %47, "
      "%48, %49, %50, %51, %52, %53, %54, %55, %56, %57, %58, %59, %60, %61, %62, %63, "
      "%64, %65, %66, %67, %68, %69, %70, %71, %72, %73, %74, %75, %76, %77, %78, %79, "
      "%80, %81, %82, %83, %84, %85, %86, %87, %88, %89, %90, %91, %92, %93, %94, %95"
      "}, da, db, p, 1, 1, 0, 1;\n}\n"
      : "+f"(d[0]), "+f"(d[1]), "+f"(d[2]), "+f"(d[3]), "+f"(d[4]), "+f"(d[5]), "+f"(d[6]), "+f"(d[7]),
        "+f"(d[8]), "+f"(d[9]), "+f"(d[10]), "+f"(d[11]), "+f"(d[12]), "+f"(d[13]), "+f"(d[14]), "+f"(d[15]),
        "+f"(d[16]), "+f"(d[17]), "+f"(d[18]), "+f"(d[19]), "+f"(d[20]), "+f"(d[21]), "+f"(d[22]), "+f"(d[23]),
        "+f"(d[24]), "+f"(d[25]), "+f"(d[26]), "+f"(d[27]), "+f"(d[28]), "+f"(d[29]), "+f"(d[30]), "+f"(d[31]),
        "+f"(d[32]), "+f"(d[33]), "+f"(d[34]), "+f"(d[35]), "+f"(d[36]), "+f"(d[37]), "+f"(d[38]), "+f"(d[39]),
        "+f"(d[40]), "+f"(d[41]), "+f"(d[42]), "+f"(d[43]), "+f"(d[44]), "+f"(d[45]), "+f"(d[46]), "+f"(d[47]),
        "+f"(d[48]), "+f"(d[49]), "+f"(d[50]), "+f"(d[51]), "+f"(d[52]), "+f"(d[53]), "+f"(d[54]), "+f"(d[55]),
        "+f"(d[56]), "+f"(d[57]), "+f"(d[58]), "+f"(d[59]), "+f"(d[60]), "+f"(d[61]), "+f"(d[62]), "+f"(d[63]),
        "+f"(d[64]), "+f"(d[65]), "+f"(d[66]), "+f"(d[67]), "+f"(d[68]), "+f"(d[69]), "+f"(d[70]), "+f"(d[71]),
        "+f"(d[72]), "+f"(d[73]), "+f"(d[74]), "+f"(d[75]), "+f"(d[76]), "+f"(d[77]), "+f"(d[78]), "+f"(d[79]),
        "+f"(d[80]), "+f"(d[81]), "+f"(d[82]), "+f"(d[83]), "+f"(d[84]), "+f"(d[85]), "+f"(d[86]), "+f"(d[87]),
        "+f"(d[88]), "+f"(d[89]), "+f"(d[90]), "+f"(d[91]), "+f"(d[92]), "+f"(d[93]), "+f"(d[94]), "+f"(d[95])
      : "r"(da), "n"(HA), "r"(db), "n"(HB), "r"(sc));
  }
};

struct FftConst {
  uint32_t f[2][4], fi[4][4];
  uint32_t ta[2][2], tb[2][2];
};
__device__ __forceinline__ void cis(int m, float scale, float& c, float& s) {
  const float a = (float)m * (-6.283185307179586f * scale);
  c = __cosf(a);
  s = __sinf(a);
}
__device__ __forceinline__ void fft_tables(uint32_t (&v)[12], int tw) {
  const int row = tw >> 2, ch = tw & 3;
#pragma unroll
  for (int i = 0; i < 4; i++) {
    float c[2], s[2], x[2];
#pragma unroll
    for (int e = 0; e < 2; e++) {
      cis((((32 * (8 * ch + 2 * i + e) + 15) * (4 * row - 63) + 2048) & 4095) - 2048, 1.f / 4096, c[e], s[e]);
      float gc, gs;
      cis((((row & 15) * (8 * (ch & 1) + 2 * i + e) + 8) & 15) - 8, 1.f / 16, gc, gs);
      x[e] = (row >> 4) == (ch >> 1) ? gc : (ch >> 1) ? gs : -gs;
    }
    v[i] = pack2(c[0] * 0.125f, c[1] * 0.125f);
    v[4 + i] = pack2(s[0] * 0.125f, s[1] * 0.125f);
    v[8 + i] = pack2(x[0], x[1]);
  }
#pragma unroll
  for (int i = 0; i < 12; i++) asm volatile("" : "+r"(v[i]));
}
__device__ __forceinline__ void fft_tables_store(const uint32_t (&v)[12], uint32_t sb, int tw) {
  const int row = tw >> 2;
  const uint32_t x = ((tw ^ (row >> 1)) & 3) << 4, a = sb + OFF_FT + (16 * (row >> 3) + (row & 7)) * 64 + x;
  sts128(a, v[0], v[1], v[2], v[3]);
  sts128(a + 512, v[4], v[5], v[6], v[7]);
  sts128(sb + OFF_GT + row * 64 + x, v[8], v[9], v[10], v[11]);
}
__device__ __forceinline__ void fft_twiddles(uint32_t (&v)[2], int tw) {
  float a[2], s[2];
#pragma unroll
  for (int i = 0; i < 2; i++) {
    float c;
    cis((2 * (2 * (tw & 3) + i) - 15) * (4 * (tw >> 2) - 63), 1.f / 4096, c, s[i]);
    a[i] = __fdividef(-s[i], 1.f + c);
  }
  v[0] = pack2(a[0], a[1]);
  v[1] = pack2(s[0], s[1]);
  asm volatile("" : "+r"(v[0]), "+r"(v[1]));
}
__device__ __forceinline__ void fft_matrices(FftConst& k, uint32_t sb, int w, int lane) {
  const uint32_t x = (lane >> 1) & 3;
  const uint2 t0 = lds64(sb + OFF_TT + 256 * w + 8 * lane), t1 = lds64(sb + OFF_TT + 256 * w + 8 * (lane ^ 3));
  k.ta[0][0] = t0.x;
  k.tb[0][0] = t0.y;
  k.ta[1][1] = __byte_perm(t1.x, 0, 0x1032);
  k.tb[1][1] = __byte_perm(t1.y, 0, 0x1032);
#pragma unroll
  for (int j = 0; j < 2; j++) {
    k.ta[1 - j][j] = k.ta[j][j] ^ 0x80008000u;
    k.tb[1 - j][j] = k.tb[j][j] ^ 0x80008000u;
    asm volatile("" : "+r"(k.ta[0][j]), "+r"(k.tb[0][j]), "+r"(k.ta[1][j]), "+r"(k.tb[1][j]));
  }
#pragma unroll
  for (int i = 0; i < 2; i++) {
    ldsm4(k.f[i], sb + OFF_FT + (16 * w + (lane & 15)) * 64 + (((2 * i + (lane >> 4)) ^ x) << 4));
    ldsm4t(k.fi[i], sb + OFF_FT + (32 * i + lane) * 64 + ((w ^ x) << 4));
#pragma unroll
    for (int j = 0; j < 4; j++) {
      k.fi[2 + i][j] = (j & 1) ? k.fi[i][j - 1] ^ 0x80008000u : k.fi[i][j + 1];
      asm volatile("" : "+r"(k.fi[2 + i][j]));
    }
  }
}
__device__ __forceinline__ void rot(uint32_t& x, uint32_t& y, uint32_t a, uint32_t b) {
  x = bfma(a, y, x);
  y = bfma(b, x, y);
  x = bfma(a, y, x);
}
__device__ __forceinline__ void twiddle_fwd(uint32_t (&a)[4][4], float* d, const FftConst& k) {
#pragma unroll
  for (int q = 0; q < 4; q++)
#pragma unroll
    for (int j = 0; j < 2; j++) {
      const float* x = d + 8 * q + 4 * j;
      uint32_t re = pack2(x[0], x[1]), im = pack2(x[2], x[3]);
      rot(re, im, k.ta[0][j], k.tb[0][j]);
      a[q & 2][2 * j + (q & 1)] = re;
      a[(q & 2) + 1][2 * j + (q & 1)] = im;
    }
}
__device__ __forceinline__ void g_step(float* d, const uint32_t (&a)[4][4], uint32_t dre, uint32_t dim) {
  WgRS<32>::set<HI_SW64>(d, a[0], dre);
  WgRS<32>::set<HI_SW64>(d + 16, a[2], dre);
  WgRS<32>::mma<HI_SW64>(d, a[1], dim);
  WgRS<32>::mma<HI_SW64>(d + 16, a[3], dim);
  wg_commit();
}

__device__ __forceinline__ void products(uint32_t (&a)[4][4], const float* H, const float* U, int p) {
#pragma unroll
  for (int j = 0; j < 2; j++)
#pragma unroll
    for (int m = 2 * p; m < 2 * p + 2; m++) {
      float pr[2], pi[2];
#pragma unroll
      for (int x = 0; x < 2; x++)
#pragma unroll
        for (int q = 0; q <= m; q++) {
          const int ih = 16 * (q >> 1) + 2 * (q & 1) + 4 * j + x, iu = 16 * ((m - q) >> 1) + 2 * ((m - q) & 1) + 4 * j + x;
          pr[x] = q ? fmaf(H[ih], U[iu], pr[x]) : H[ih] * U[iu];
          pi[x] = q ? fmaf(H[ih], U[iu + 8], pi[x]) : H[ih] * U[iu + 8];
          pr[x] = fmaf(-H[ih + 8], U[iu + 8], pr[x]);
          pi[x] = fmaf(H[ih + 8], U[iu], pi[x]);
        }
      a[m & 2][2 * j + (m & 1)] = pack2(pr[0], pr[1]);
      a[(m & 2) + 1][2 * j + (m & 1)] = pack2(pi[0], pi[1]);
    }
}

__device__ __forceinline__ void f_step(float* d, const FftConst& k, uint32_t db) {
  WgRS<64>::set<HI_SW32>(d, k.f[0], db);
  WgRS<64>::mma<HI_SW32>(d, k.f[1], db + 32);
  wg_commit();
}
__device__ __forceinline__ void last_step(float* d, const FftConst& k, uint32_t dz) {
  wg_fence();
  WgRS<64>::set<HI_SW128>(d, k.fi[0], dz);
#pragma unroll
  for (int ks = 1; ks < 4; ks++) WgRS<64>::mma<HI_SW128>(d, k.fi[ks], dz + 128 * ks);
  wg_commit();
}
__device__ __forceinline__ void conv_channel(const FftConst& k, uint32_t (&a)[4][4], uint32_t sb, int c, int cn, int wg, int w, int lane) {
  const uint32_t cb = sb + off_ch(c), bars = sb + OFF_BAR;
  const uint32_t du = desc_lo(cb, 1024), dg = desc_lo(sb + OFF_GT, 16), dz = desc_lo(cb + U_BYTES, 16);
  float U[32], H[32];
  uint32_t e[4][4];
  const float dv = __uint_as_float(lds32(sb + OFF_D + 4 * c));
  if (ATT_GATE) mbar_wait(bars + 8 * (ATT_GATE == 1 ? B_ATTN : B_ATT2), 0);
  mbar_wait(bars + 8 * (B_U + (c < 3 ? c : 3)), 0);
  TSM(w == 0 && c < 3, 7 + wg);
  wg_fence();
  f_step(U, k, du);
  g_step(H, a, dg, dg + 64);
  wg_wait<1>();
  pin<32>(U);
  twiddle_fwd(e, U, k);
  wg_fence();
  g_step(U, e, dg, dg + 64);
  wg_wait<0>();
  pin<32>(U);
  pin<32>(H);
#pragma unroll
  for (int j = 0; j < 4; j++) H[4 * (j >> 1) + (j & 1)] += dv;
  float V[32];
#pragma unroll
  for (int p = 0; p < 2; p++) {
    products(a, H, U, p);
    wg_fence();
    WgRS<32>::set<HI_SW64>(V + 16 * p, a[2 * p], dg + 64);
    WgRS<32>::mma<HI_SW64>(V + 16 * p, a[2 * p + 1], dg);
    wg_commit();
  }
  const uint32_t za = cb + U_BYTES + (8 * w + (lane & 7)) * 128 + (((lane >> 3) ^ (lane & 7)) << 4);
  const uint32_t ya = cb + (lane >> 4) * 1024 + (8 * w + (lane & 7)) * 32 + ((((lane >> 3) ^ (lane >> 2)) & 1) << 4);
  wg_sync(1 + wg);
#pragma unroll
  for (int p = 0; p < 2; p++) {
    if (p == 0) wg_wait<1>();
    else wg_wait<0>();
    pin<16>(V + 16 * p);
#pragma unroll
    for (int i = 0; i < 4; i++) {
      const int j = i & 1;
      const float* x = V + 16 * p + 4 * j + (i & 2);
      e[p][i] = pack2(x[8], x[9]);
      e[2 + p][i] = pack2(x[0], x[1]);
      rot(e[p][i], e[2 + p][i], k.ta[1][j], k.tb[1][j]);
    }
    stsm4(za ^ (64 * p), e[p]);
    stsm4((za ^ (64 * p)) + 4096, e[2 + p]);
  }
  if (cn >= 0) {
    wg_fence();
    f_step(U, k, desc_lo(sb + off_ch(cn) + U_BYTES, 1024));
    fence_async_smem();
    wg_sync(1 + wg);
    last_step(H, k, dz);
    wg_wait<1>();
    pin<32>(U);
    twiddle_fwd(a, U, k);
    wg_wait<0>();
  } else {
    fence_async_smem();
    wg_sync(1 + wg);
    last_step(H, k, dz);
    wg_wait<0>();
  }
  pin<32>(H);
  if (WO_GATE == 4 && lane == 0) mbar_arrive(bars + 8 * B_CVD);
  TSIF(w == 0, 88 + c);
#pragma unroll
  for (int j = 0; j < 8; j++)
    e[j >> 2][j & 3] = j < 2 ? pack2(H[4 * j], H[4 * j + 1]) : pack2(H[4 * j] + H[4 * j - 6], H[4 * j + 1] + H[4 * j - 5]);
  stsm4(ya, e[0]);
  stsm4(ya + 2048, e[1]);
  fence_async_smem();
  __syncwarp();
}

__device__ __forceinline__ void prep_slab(uint4* res, const uint2* sw, uint32_t sb, int slab, int w, int lane) {
  const int t = lane & 3, tp = (lane & 7) >> 1, pos = 8 * tp + 2 * (((lane >> 3) + tp) & 3) + (lane & 1);
  const uint32_t base = sb + OFF_KVS + slab * KVS_BYTES + pos * 128;
  uint32_t kk[2][4][4], vv[2][4];
  mbar_wait(sb + OFF_BAR + 8 * (B_KV + slab), 0);
#pragma unroll
  for (int h = 0; h < 2; h++) {
#pragma unroll
    for (int j = 0; j < 4; j++) {
      const uint32_t a = base + 128 * j;
      ldsm4t(kk[h][j], a + (((w + 4 * h) ^ ((a >> 7) & 7)) << 4));
    }
    const uint32_t a = base + KVS_V;
    ldsm4t(vv[h], a + (((w + 4 * h) ^ ((a >> 7) & 7)) << 4));
  }
#pragma unroll
  for (int h = 0; h < 2; h++) {
    uint32_t (&k)[4][4] = kk[h];
    uint32_t (&v)[4] = vv[h];
    const uint32_t w0 = __byte_perm(sw[h].x, 0, 0x1010), w1 = __byte_perm(sw[h].x, 0, 0x3232);
    const uint32_t w2 = __byte_perm(sw[h].y, 0, 0x1010), w3 = __byte_perm(sw[h].y, 0, 0x3232);
#pragma unroll
    for (int m = 0; m < 4; m++)
      v[m] = bmul(badd(badd(badd(bmul(k[0][m], w3), bmul(k[1][m], w2)), bmul(k[2][m], w1)), bmul(k[3][m], w0)), v[m]);
    uint32_t a[4];
#pragma unroll
    for (int m = 0; m < 4; m++) a[m] = (t & 1) ? v[(m + 3) & 3] : v[m];
    res[h] = (t & 2) ? make_uint4(a[2], a[3], a[0], a[1]) : make_uint4(a[0], a[1], a[2], a[3]);
  }
}

__device__ __forceinline__ void prep_gate(const Params& p, uint32_t sb, int b, int w, int lane) {
  uint2 gw[5], x[4][5];
#pragma unroll
  for (int j = 0; j < 5; j++) gw[j] = ldg64(reinterpret_cast<const uint2*>(p.gate_w) + lane + 32 * j);
#pragma unroll
  for (int i = 0; i < 4; i++)
#pragma unroll
    for (int j = 0; j < 5; j++)
      x[i][j] = ldg64(reinterpret_cast<const uint2*>(p.q) + (16 * b + 4 * w + i) * (DIM / 4) + lane + 32 * j);
  float s[4];
#pragma unroll
  for (int i = 0; i < 4; i++) {
    s[i] = 0.f;
#pragma unroll
    for (int j = 0; j < 5; j++) {
      const uint32_t m0 = bmul(x[i][j].x, gw[j].x), m1 = bmul(x[i][j].y, gw[j].y);
      s[i] += (bf_lo(m0) + bf_hi(m0)) + (bf_lo(m1) + bf_hi(m1));
    }
  }
  const bool h = lane & 16, q = lane & 8;
  const float a = (h ? s[2] : s[0]) + __shfl_xor_sync(0xffffffffu, h ? s[0] : s[2], 16);
  const float c = (h ? s[3] : s[1]) + __shfl_xor_sync(0xffffffffu, h ? s[1] : s[3], 16);
  float z = (q ? c : a) + __shfl_xor_sync(0xffffffffu, q ? a : c, 8);
#pragma unroll
  for (int o = 4; o > 0; o >>= 1) z += __shfl_xor_sync(0xffffffffu, z, o);
  z = bf_lo(pack2(z, 0.f));
  z = bf_lo(pack2(__fdividef(1.f, 1.f + __expf(-z)), 0.f));
  if (G_TMA) {
    mbar_wait(sb + OFF_BAR + 8 * B_S3, 0);
    if ((lane & 7) == 0) asm volatile("st.shared.f32 [%0], %1;" ::"r"(sb + OFF_GATE + 64 * (b & 7) + 16 * w + (lane >> 1)), "f"(z) : "memory");
    fence_async_smem();
  } else if ((lane & 7) == 0) {
    g_gate[16 * b + 4 * w + (lane >> 3)] = z;
  }
}

__device__ __forceinline__ uint32_t bmax(uint32_t a, uint32_t b) {
  uint32_t d;
  asm("max.bf16x2 %0, %1, %2;" : "=r"(d) : "r"(a), "r"(b));
  return d;
}
__device__ __forceinline__ void softmax_two(const float (&l)[2][2], uint32_t& p0, uint32_t& p1) {
  constexpr float kScale = 0.22360679774997896f, kLog2e = 1.4426950408889634f;
  const uint32_t r0 = pack2(l[0][0], l[1][0]), r1 = pack2(l[0][1], l[1][1]);
  const uint32_t x0 = pack2(bf_lo(r0) * kScale, bf_hi(r0) * kScale), x1 = pack2(bf_lo(r1) * kScale, bf_hi(r1) * kScale);
  uint32_t m = bmax(x0, x1);
  m = bmax(m, __shfl_xor_sync(0xffffffffu, m, 1));
  m = bmax(m, __shfl_xor_sync(0xffffffffu, m, 2));
  const float m0 = bf_lo(m) * kLog2e, m1 = bf_hi(m) * kLog2e;
  p0 = pack2(ex2(bf_lo(x0) * kLog2e - m0), ex2(bf_lo(x1) * kLog2e - m0));
  p1 = pack2(ex2(bf_hi(x0) * kLog2e - m1), ex2(bf_hi(x1) * kLog2e - m1));
}

__device__ __forceinline__ void halo_read(uint32_t (&kpv)[10], uint32_t (&vpv)[10], uint32_t (&tg)[7], const uint4* hp) {
#pragma unroll
  for (int j = 0; j < 7; j++) {
    uint32_t x0, x1, x2;
    asm volatile("ld.relaxed.gpu.global.v4.u32 {%0, %1, %2, %3}, [%4];"
                 : "=r"(x0), "=r"(x1), "=r"(x2), "=r"(tg[j]) : "l"(hp + 32 * j) : "memory");
    if (j < 4) kpv[3 * j] = x0; else vpv[3 * j - 10] = x0;
    if (j < 3) kpv[3 * j + 1] = x1; else vpv[3 * j - 9] = x1;
    if (j < 3) kpv[3 * j + 2] = x2; else if (j < 6) vpv[3 * j - 8] = x2;
  }
}

template <int ROT>
__device__ __forceinline__ void pack_qkv(const float* acc, uint32_t (&qlo)[10], uint32_t (&qhi)[10], uint32_t (&klo)[10],
                                         uint32_t (&khi)[10], uint32_t (&vlo)[10], uint32_t (&vhi)[10]) {
#pragma unroll
  for (int j = 0; j < 10; j++) {
    const int x = (j + ROT) % 10, tq = x < 8 ? x : 16 + x, tk = x < 8 ? 8 + x : 18 + x, tv = x < 8 ? 16 + x : 20 + x;
    khi[j] = pack2(acc[4 * tk + 2], acc[4 * tk + 3]);
    vhi[j] = movm(pack2(acc[4 * tv + 2], acc[4 * tv + 3]));
    qlo[j] = pack2(acc[4 * tq], acc[4 * tq + 1]);
    qhi[j] = pack2(acc[4 * tq + 2], acc[4 * tq + 3]);
    klo[j] = pack2(acc[4 * tk], acc[4 * tk + 1]);
    vlo[j] = pack2(acc[4 * tv], acc[4 * tv + 1]);
    asm volatile("" : "+r"(khi[j]), "+r"(qlo[j]), "+r"(qhi[j]), "+r"(klo[j]), "+r"(vlo[j]));
  }
}

template <int ROT> __device__ __forceinline__ void halo_send(const float* acc, uint4* ho, uint32_t tag) {
#pragma unroll
  for (int j = 0; j < 7; j++) {
    uint32_t x[3];
#pragma unroll
    for (int e = 0; e < 3; e++) {
      const int i = 3 * j + e, y = (i % 10 + ROT) % 10, tk = y < 8 ? 8 + y : 18 + y, tv = y < 8 ? 16 + y : 20 + y;
      x[e] = i < 10 ? pack2(acc[4 * tk + 2], acc[4 * tk + 3]) : i < 20 ? movm(pack2(acc[4 * tv + 2], acc[4 * tv + 3])) : 0u;
    }
    asm volatile("st.relaxed.gpu.global.v4.u32 [%0], {%1, %2, %3, %4};" ::"l"(ho + 32 * j), "r"(x[0]), "r"(x[1]), "r"(x[2]), "r"(tag) : "memory");
  }
}

__device__ __forceinline__ void attention(float* acc, uint32_t sb, int b, int par, int w, int lane, uint32_t tag, uint32_t zero) {
  const int g = lane >> 2, t = lane & 3;
  uint32_t klo[10], khi[10], vlo[10], vhi[10], qlo[10], qhi[10], kpv[10], vpv[10];
  if (HALO_FIRST && w == 3 && b < NCTA - 8) {
    uint4* ho = g_halo + (b * 2 + par) * 224 + lane;
    if (tail_first(b & 7)) halo_send<8>(acc, ho, tag);
    else halo_send<0>(acc, ho, tag);
    TSIF(par == 0, 76);
    pin<120>(acc);
  }
  if (tail_first(b & 7)) pack_qkv<8>(acc, qlo, qhi, klo, khi, vlo, vhi);
  else pack_qkv<0>(acc, qlo, qhi, klo, khi, vlo, vhi);
  const uint32_t xa = sb + OFF_KVX + (par * 3) * 2560 + lane * 16;
  if (w < 3) {
    sts128(xa + w * 2560, khi[0], khi[1], khi[2], khi[3]);
    sts128(xa + w * 2560 + 512, khi[4], khi[5], khi[6], khi[7]);
    sts128(xa + w * 2560 + 1024, khi[8], khi[9], vhi[0], vhi[1]);
    sts128(xa + w * 2560 + 1536, vhi[2], vhi[3], vhi[4], vhi[5]);
    sts128(xa + w * 2560 + 2048, vhi[6], vhi[7], vhi[8], vhi[9]);
  } else if (!HALO_FIRST && b < NCTA - 8) {
    uint4* ho = g_halo + (b * 2 + par) * 224 + lane;
#pragma unroll
    for (int j = 0; j < 7; j++) {
      const uint32_t x0 = j < 4 ? khi[3 * j] : vhi[3 * j - 10], x1 = j < 3 ? khi[3 * j + 1] : vhi[3 * j - 9];
      const uint32_t x2 = j < 3 ? khi[3 * j + 2] : j < 6 ? vhi[3 * j - 8] : 0u;
      asm volatile("st.relaxed.gpu.global.v4.u32 [%0], {%1, %2, %3, %4};" ::"l"(ho + 32 * j), "r"(x0), "r"(x1), "r"(x2), "r"(tag) : "memory");
    }
  }
  TSIF(par == 0 && w == 1, 64);
  TSIF(par == 0 && w == 3 && !HALO_FIRST, 76);
#pragma unroll
  for (int j = 0; j < 10; j++) vlo[j] = movm(vlo[j]);
  const bool far0 = 2 * t > g, far1 = 2 * t + 1 > g;
  const uint32_t mfar = (far0 ? 0x0000FFFFu : 0u) | (far1 ? 0xFFFF0000u : 0u);
  float slo[4][2], shi[4][2], lg[2][2];
  uint32_t phi[4], plo[4], qml[4], qmh[4];
#pragma unroll
  for (int h = 0; h < 4; h++) {
    const int f = h == 0 ? 0 : h == 1 ? 3 : h == 2 ? 5 : 8, hf = h < 2 ? 2 : 7;
    const bool mine = (h & 1) ? t >= 2 : t < 2;
    qml[h] = mine ? qlo[hf] : 0u;
    qmh[h] = mine ? qhi[hf] : 0u;
    float a[4] = {0.f, 0.f, 0.f, 0.f}, c[4] = {0.f, 0.f, 0.f, 0.f};
    mma16816(a, qlo[f], qhi[f], qlo[f + 1], qhi[f + 1], klo[f], klo[f + 1]);
    mma16816(c, qlo[f], qhi[f], qlo[f + 1], qhi[f + 1], khi[f], khi[f + 1]);
    mma1688(a, qml[h], qmh[h], klo[hf]);
    mma1688(c, qml[h], qmh[h], khi[hf]);
    slo[h][0] = a[0];
    slo[h][1] = a[1];
    shi[h][0] = lg[h & 1][0] = far0 ? a[2] : c[2];
    shi[h][1] = lg[h & 1][1] = far1 ? a[3] : c[3];
    if (!ATT_MERGE && (h & 1)) softmax_two(lg, phi[h - 1], phi[h]);
  }
  TSIF(par == 0 && w == 1, 65);
  if (ATT_GATE == 3 && lane == 0) mbar_arrive(sb + OFF_BAR + 8 * B_ATT2 + (phi[3] & zero));
  wg_sync(1 + par);
  TSIF(par == 0 && w == 1, 66);
  const bool nohist = (w == 0) && (b < 8);
  const uint4* hp = g_halo + ((b - 8) * 2 + par) * 224 + lane;
  uint32_t tg[7];
  if (w > 0) {
    const uint4 v0 = lds128(xa + (w - 1) * 2560), v1 = lds128(xa + (w - 1) * 2560 + 512), v2 = lds128(xa + (w - 1) * 2560 + 1024);
    const uint4 v3 = lds128(xa + (w - 1) * 2560 + 1536), v4 = lds128(xa + (w - 1) * 2560 + 2048);
    kpv[0] = v0.x; kpv[1] = v0.y; kpv[2] = v0.z; kpv[3] = v0.w; kpv[4] = v1.x; kpv[5] = v1.y; kpv[6] = v1.z; kpv[7] = v1.w;
    kpv[8] = v2.x; kpv[9] = v2.y; vpv[0] = v2.z; vpv[1] = v2.w; vpv[2] = v3.x; vpv[3] = v3.y; vpv[4] = v3.z; vpv[5] = v3.w;
    vpv[6] = v4.x; vpv[7] = v4.y; vpv[8] = v4.z; vpv[9] = v4.w;
  } else if (nohist) {
#pragma unroll
    for (int j = 0; j < 10; j++) kpv[j] = vpv[j] = 0u;
  } else {
    TSIF(par == 0, 77);
    halo_read(kpv, vpv, tg, hp);
  }
  if (w == 0 && !nohist) {
    int spins = 0;
    while (true) {
      bool ok = true;
#pragma unroll
      for (int j = 0; j < 7; j++) ok = ok && tg[j] == tag;
      if (__all_sync(0xffffffffu, ok) || ++spins > SPIN_LIMIT) break;
      halo_read(kpv, vpv, tg, hp);
    }
    TSIF(par == 0, 79);
  }
#pragma unroll
  for (int h = 0; h < 4; h++) {
    const int f = h == 0 ? 0 : h == 1 ? 3 : h == 2 ? 5 : 8, hf = h < 2 ? 2 : 7;
    float a[4] = {0.f, 0.f, 0.f, 0.f};
    mma16816(a, qlo[f], qhi[f], qlo[f + 1], qhi[f + 1], kpv[f], kpv[f + 1]);
    mma1688(a, qml[h], qmh[h], kpv[hf]);
    const float ninf = __int_as_float(0xff800000);
    lg[h & 1][0] = far0 ? (nohist ? ninf : a[0]) : slo[h][0];
    lg[h & 1][1] = far1 ? (nohist ? ninf : a[1]) : slo[h][1];
    if (h & 1) {
      softmax_two(lg, plo[h - 1], plo[h]);
      if (ATT_MERGE) {
        const float lh[2][2] = {{shi[h - 1][0], shi[h - 1][1]}, {shi[h][0], shi[h][1]}};
        softmax_two(lh, phi[h - 1], phi[h]);
      }
    }
  }
  TSIF(par == 0 && w <= 1, 67 + w);
  if (ATT_GATE == 2 && lane == 0) mbar_arrive(sb + OFF_BAR + 8 * B_ATT2 + (plo[3] & zero));
  uint32_t ov[20];
#pragma unroll
  for (int hp = 0; hp < 2; hp++) {
    const int hf = hp ? 7 : 2;
    float sh[4] = {0.f, 0.f, 0.f, 0.f}, i0 = 0.f, i1 = 0.f;
#pragma unroll
    for (int e = 0; e < 2; e++) {
      const int h = 2 * hp + e, f = h == 0 ? 0 : h == 1 ? 3 : h == 2 ? 5 : 8;
      const uint32_t a0 = plo[h] & mfar, a2 = plo[h] & ~mfar, a3 = phi[h] & mfar, c1 = phi[h] & ~mfar;
      float sum[4] = {0.f, 0.f, 0.f, 0.f};
      mma1688(sum, plo[h], phi[h], 0x3F803F80u);
      const float r0 = rcp(sum[0]), r1 = rcp(sum[2]);
#pragma unroll
      for (int j = f; j < f + 2; j++) {
        float o[4] = {0.f, 0.f, 0.f, 0.f};
        mma16816(o, a0, 0u, a2, a3, vpv[j], vlo[j]);
        mma1688(o, 0u, c1, vhi[j]);
        ov[2 * j] = pack2(o[0] * r0, o[1] * r0);
        ov[2 * j + 1] = pack2(o[2] * r1, o[3] * r1);
      }
      const bool mine = e ? g >= 4 : g < 4;
      mma16816(sh, a0, 0u, a2, a3, mine ? vpv[hf] : 0u, mine ? vlo[hf] : 0u);
      mma1688(sh, 0u, c1, mine ? vhi[hf] : 0u);
      if (e == 0 || t >= 2) {
        i0 = r0;
        i1 = r1;
      }
    }
    ov[2 * hf] = pack2(sh[0] * i0, sh[1] * i0);
    ov[2 * hf + 1] = pack2(sh[2] * i1, sh[3] * i1);
  }
  if (ATT_GATE == 4 && lane == 0) mbar_arrive(sb + OFF_BAR + 8 * B_ATT2 + (ov[19] & zero));
  TS(32 + 4 * par + w);
  mbar_wait(sb + OFF_BAR + 8 * B_P1, 0);
  const uint32_t oa = sb + OFF_OA + (lane >> 4) * 2048 + (32 * w + 2 * (lane & 15) + par) * 16;
#pragma unroll
  for (int j = 0; j < 5; j++) stsm4(oa + 4096 * j, ov + 4 * j);
  TSIF(par == 0 && w == 0, 120);
  fence_async_smem();
  TSIF(par == 0 && w == 0, 121);
  __syncwarp();
  if (lane == 0) mbar_arrive(sb + OFF_BAR + 8 * B_ATTN);
  TSM(w == 0 || w == 2, 122 + par + (w == 2 ? 3 : 0));
}

struct Maps {
  CUtensorMap x, wm, wt, k, v, y, wo, qm, qt, om, ot, u;
};

__device__ __forceinline__ void load_stage(uint32_t sb, int kb, int b, const Maps& m) {
  const uint32_t st = sb + (kb & 3) * STAGE_BYTES, bar = sb + OFF_BAR + 8 * (B_FULL1 + (kb & 3));
  const int r = b >> 3, hg = b & 7, slab = kb - KV_KB;
  const bool kv = slab >= 0 && slab < 5;
  const uint32_t kbar = sb + OFF_BAR + 8 * (B_KV + slab), dst = sb + OFF_KVS + slab * KVS_BYTES;
  mbar_expect_tx(bar, STAGE_BYTES);
  if (kv) mbar_expect_tx(kbar, KVS_BYTES);
  tma_3d(st, &m.x, 64 * kb, 64 * r, 0, bar);
  if (kv && KV_MIX) tma_3d(dst, &m.k, 0, 32 * (b >> 1) - 3, 2 * slab + (b & 1), kbar);
  tma_3d(st + ST_W, &m.wm, 80 * hg + (tail_first(hg) ? 16 : 0), 64 * kb, 0, bar);
  if (kv && KV_MIX) tma_3d(dst + KVS_V, &m.v, 0, 32 * (b >> 1), 2 * slab + (b & 1), kbar);
  tma_3d(st + ST_WT, &m.wt, 80 * hg + (tail_first(hg) ? 0 : 64), 64 * kb, 0, bar);
  if (kv && !KV_MIX) tma_3d(dst, &m.k, 0, 32 * (b >> 1) - 3, 2 * slab + (b & 1), kbar);
  if (kv && !KV_MIX) tma_3d(dst + KVS_V, &m.v, 0, 32 * (b >> 1), 2 * slab + (b & 1), kbar);
}

__global__ void __launch_bounds__(NTHR, 1) fused_kernel(const __grid_constant__ Maps m, const Params p) {
  extern __shared__ __align__(1024) uint8_t smem[];
  const uint32_t sb = (uint32_t)__cvta_generic_to_shared(smem);
  const uint32_t bars = sb + OFF_BAR;
  const int tid = threadIdx.x, lane = tid & 31;
  int b = blockIdx.x;
  if (BMAP == 1) b = (((b & 63) >> 3) * 2 + (b & 1)) * 8 + (((b < 64 ? 0x6521 : 0x7430) >> (4 * ((b >> 1) & 3))) & 7);
  if (BMAP == 2) b = ((b & 63) >> 2) * 8 + (((b < 64 ? 0x6521 : 0x7430) >> (4 * (b & 3))) & 7);
  if (BMAP == 3) b = (((b & 63) >> 3) * 2 + (b & 1)) * 8 + (((b < 64 ? 0x7430 : 0x6521) >> (4 * ((b >> 1) & 3))) & 7);
  if (BMAP == 4) b = (((b >> 4) * 2 + (b & 1)) * 8) + ((b >> 1) & 7);
  if (BMAP == 5) b = 127 - b;
  const int r = b >> 3, hg = b & 7;

  if (tid == T_ISSUE) {
    TSM(true, 0);
#pragma unroll
    for (int i = 0; i < 4; i++) mbar_init(bars + 8 * (B_FULL1 + i), 1);
#pragma unroll
    for (int i = 0; i < 3; i++) mbar_init(bars + 8 * (B_KV + i), 1);
    fence_async_smem();
#pragma unroll 1
    for (int kb = 0; kb <= PRE2; kb++) load_stage(sb, kb, b, m);
  } else if (tid >= T_PF && tid < T_PF + 12) {
    tm_prefetch(&m.x + (tid - T_PF));
  } else if (tid == T_INIT) {
#pragma unroll
    for (int i = 0; i < 4; i++) mbar_init(bars + 8 * (B_EMPTY1 + i), 8);
#pragma unroll
    for (int i = 0; i < 8; i++) mbar_init(bars + 8 * (B_FULL2 + i), 1);
#pragma unroll
    for (int i = 0; i < 4; i++) mbar_init(bars + 8 * (B_EMPTY2 + i), 8);
#pragma unroll
    for (int i = 0; i < 4; i++) mbar_init(bars + 8 * (B_U + i), 1);
    mbar_init(bars + 8 * B_HA, 4);
    mbar_init(bars + 8 * B_GATE, 4);
    mbar_init(bars + 8 * B_HB, 1);
    mbar_init(bars + 8 * B_KVD, 4);
    mbar_init(bars + 8 * B_QF, 1);
    mbar_init(bars + 8 * B_ATTN, 8);
    mbar_init(bars + 8 * B_ATT2, 8);
    mbar_init(bars + 8 * B_P1, 8);
    mbar_init(bars + 8 * B_C34, 1);
    mbar_init(bars + 8 * B_YRB, 1);
#pragma unroll
    for (int i = 0; i < 5; i++) mbar_init(bars + 8 * (B_YST + i), 4);
#pragma unroll
    for (int i = 0; i < 5; i++) mbar_init(bars + 8 * (B_US + i), i == 2 ? 20 : i == 1 ? 8 : 1);
    mbar_init(bars + 8 * B_YSIG, 1);
    mbar_init(bars + 8 * B_YFULL, 1);
    mbar_init(bars + 8 * B_EPOCH, 1);
    mbar_init(bars + 8 * B_PREP, 4);
    mbar_init(bars + 8 * B_USIG, 1);
    mbar_init(bars + 8 * B_WST, 1);
#pragma unroll
    for (int i = 3; i < 5; i++) mbar_init(bars + 8 * (B_KV + i), 1);
    mbar_init(bars + 8 * B_E3, 8);
    mbar_init(bars + 8 * B_LAST, 1);
    mbar_init(bars + 8 * B_OSIG, 1);
    mbar_init(bars + 8 * B_WOP, 1);
    fence_async_smem();
  }
  const int warp = __shfl_sync(0xffffffffu, tid >> 5, 0), wg = warp >> 2, w = warp & 3;
  __syncthreads();

  if (wg == 3) {
    asm volatile("setmaxnreg.dec.sync.aligned.u32 56;");
    if (w == 0) {
      if (lane == 0) {
#pragma unroll 1
        for (int kb = 1 + PRE2; kb < 10; kb++) {
          if (kb >= 4) mbar_wait(bars + 8 * (kb == 7 ? B_E3 : B_EMPTY1 + (kb & 3)), (kb >> 3) & 1);
          TSIF(kb >= 4, 44 + kb);
          load_stage(sb, kb, b, m);
          TSIF(kb == 3, 60);
          if (kb == TRIG_KB) mbar_arrive(bars + 8 * B_LAST);
        }
        mbar_wait(bars + 8 * B_WOP, 0);
        mbar_wait(bars + 8 * WL_TRIG, 0);
        mbar_wait(bars + 8 * B_EPOCH, 0);
        flag_wait(g_cnt + C_W + 32 * hg, (lds32(sb + OFF_EPOCH) + 1) * 16);
        TS(30);
#pragma unroll 1
        for (int j = 0; j < 8; j++) {
          if (Q_REG && j == Q_AT) {
            mbar_expect_tx(bars + 8 * B_QF, O_BYTES);
            tma_2d(sb + OFF_QS, &m.qm, 80 * hg, 128 * r, bars + 8 * B_QF);
            tma_2d(sb + OFF_QT, &m.qt, 80 * hg + 64, 128 * r, bars + 8 * B_QF);
          }
          if (j >= 6) mbar_wait(bars + 8 * (B_EMPTY2 + j - 6), 0);
          if (j == 4) mbar_wait(bars + 8 * B_ATTN, 0);
          TSIF(j >= 6, 100 + j);
          if (RF_GATE && j == 6) mbar_wait(bars + 8 * B_YSIG, 0);
          mbar_expect_tx(bars + 8 * (B_FULL2 + j), j == 0 ? WO_BYTES : j == 5 ? O_BYTES + WO_BYTES + 512 : O_BYTES + WO_BYTES);
          bulk_load(sb + off_w(j), g_WO + (hg * 8 + step_src(hg, j)) * 800, WO_BYTES, bars + 8 * (B_FULL2 + j));
        }
        if (!Q_REG) {
          mbar_wait(bars + 8 * (B_EMPTY2 + Q_SLOT), 0);
          mbar_expect_tx(bars + 8 * B_QF, O_BYTES);
          tma_2d(sb + OFF_QS, &m.qm, 80 * hg, 128 * r, bars + 8 * B_QF);
          tma_2d(sb + OFF_QT, &m.qt, 80 * hg + 64, 128 * r, bars + 8 * B_QF);
        }
      }
    } else if (w == 1) {
      unsigned epoch = 0;
      if (lane == 0) {
        epoch = atomicAdd(g_cnt + C_LAUNCH, 1u) / NCTA;
        asm volatile("st.shared.u32 [%0], %1;" ::"r"(sb + OFF_EPOCH), "r"(epoch) : "memory");
        mbar_arrive(bars + 8 * B_EPOCH);
        mbar_wait(bars + 8 * B_KVD, 0);
        mbar_expect_tx(bars + 8 * B_HB, 5 * 4096);
#pragma unroll 1
        for (int c = 0; c < 5; c++) {
          if (c == 3) mbar_wait(bars + 8 * B_S3, 0);
          bulk_load(sb + off_ch(c) + U_BYTES, p.ssm_k + (5 * b + c) * SEQ, 4096, bars + 8 * B_HB);
        }
#pragma unroll
        for (int c = 0; c < 4; c++) mbar_expect_tx(bars + 8 * (B_U + c), c < 3 ? U_BYTES : 2 * U_BYTES);
        const uint4* usrc = g_U + 5 * b * U_PITCH;
        mbar_wait(bars + 8 * B_USIG, 0);
        flag_wait(g_cnt + C_PREP + 32 * (b & 15), (epoch + 1) * NCTA);
        TS(23);
#pragma unroll
        for (int c = 0; c < 5; c++) {
          if (c == 3 && U_TRIM) mbar_wait(bars + 8 * (B_U + 2), 0);
          bulk_load(sb + off_ch(c), usrc + c * U_PITCH, U_BYTES, bars + 8 * (B_U + (c < 3 ? c : 3)));
          TSIF(c == 0 || c == 4, 116 + (c >> 2));
        }
      }
      epoch = __shfl_sync(0xffffffffu, epoch, 0);
      if (lane < 8) {
        const int src = (b & ~7) | step_src(hg, lane);
        mbar_wait(bars + 8 * OP_TRIG, 0);
        TS(20);
        bool seen = false;
#pragma unroll 1
        for (int spins = 0; spins < SPIN_LIMIT; spins++) {
          const bool now = !seen && (int)(flag_read(g_cnt + C_O + 32 * src) - (epoch + 1)) >= 0;
          if (now && lane >= 1 && lane < (Q_REG ? 3 : 4)) bulk_load(sb + off_o(lane), g_O + src * 1280, O_BYTES, bars + 8 * (B_FULL2 + lane));
          seen = seen || now;
          if (__all_sync(0xff, seen)) break;
        }
        TS(21);
        if (lane == 5) bulk_load(sb + OFF_GATE, g_gate + 128 * r, 512, bars + 8 * (B_FULL2 + 5));
#pragma unroll 1
        for (int j = Q_REG ? 3 : 4; j < 8; j++) {
          if (lane == j) {
            mbar_wait(bars + 8 * (j == (Q_REG == 2 ? 5 : 3) ? B_QE : j < 6 ? B_C34 : B_EMPTY2 + j - 6), 0);
            if (RF_GATE && j == 6) mbar_wait(bars + 8 * B_YSIG, 0);
            bulk_load(sb + off_o(j), g_O + src * 1280, O_BYTES, bars + 8 * (B_FULL2 + j));
          }
          __syncwarp(0xff);
        }
        TS(22);
      }
    } else if (w == 2) {
      mbar_wait(bars + 8 * B_PREP, 0);
      flag_signal(g_cnt + C_PREP, 16, lane);
      TS(25);
      if (lane == 0) {
        mbar_arrive(bars + 8 * B_USIG);
        mbar_expect_tx(bars + 8 * B_ORB, O_BYTES + 64);
        mbar_wait(bars + 8 * B_GATE, 0);
        bulk_store(g_gate + 16 * b, sb + OFF_GATE + 64 * hg, 64);
        bulk_wait_read<0>();
        bulk_load(sb + OFF_GATE + 64 * hg, g_gate + 16 * b, 64, bars + 8 * B_ORB);
        mbar_wait(bars + 8 * B_ATTN, 0);
        constexpr uint32_t PB = O_BYTES / O_SPLIT;
#pragma unroll
        for (int i = 0; i < O_SPLIT; i++) bulk_store(g_O + b * 1280 + i * (PB / 16), sb + OFF_OA + i * PB, PB);
#pragma unroll
        for (int i = 0; i < O_SPLIT; i++) {
          if (O_SPLIT - 1 - i == 4) bulk_wait_read<4>();
          if (O_SPLIT - 1 - i == 3) bulk_wait_read<3>();
          if (O_SPLIT - 1 - i == 2) bulk_wait_read<2>();
          if (O_SPLIT - 1 - i == 1) bulk_wait_read<1>();
          if (O_SPLIT - 1 - i == 0) bulk_wait_read<0>();
          bulk_load(sb + OFF_OA + i * PB, g_O + b * 1280 + i * (PB / 16), PB, bars + 8 * B_ORB);
        }
        TS(74);
        mbar_wait(bars + 8 * B_ORB, 0);
        flag_bump(g_cnt + C_O + 32 * b);
        TS(26);
        mbar_arrive(bars + 8 * B_OSIG);
      }
    } else {
      if (lane == 0) {
        uint4* dst = g_WO + (hg * 8 + (r >> 1)) * 800 + (r & 1) * 80;
        if (WPF) {
          mbar_wait(bars + 8 * WPF, 0);
          if (WPF_LIN)
            asm volatile("cp.async.bulk.prefetch.L2.global [%0], 6400;" ::"l"(p.wo + b * 3200) : "memory");
          else
            asm volatile("cp.async.bulk.prefetch.tensor.3d.L2.global [%0, {%1, %2, %3}];" ::"l"(&m.wo), "r"(0), "r"(40 * r), "r"(5 * hg) : "memory");
        }
        mbar_wait(bars + 8 * B_P1, 0);
        mbar_wait(bars + 8 * WB_TRIG, 0);
        mbar_expect_tx(bars + 8 * B_WST, WO_BYTES / 2);
        tma_3d(sb + OFF_WS, &m.wo, 0, 40 * r, 5 * hg, bars + 8 * B_WST);
        mbar_wait(bars + 8 * B_WST, 0);
        mbar_wait(bars + 8 * WO_TRIG, 0);
#pragma unroll 1
        for (int n = 0; n < 5; n++)
          asm volatile("cp.async.bulk.global.shared::cta.bulk_group [%0], [%1], 1280;" ::"l"(dst + 160 * n), "r"(sb + OFF_WS + 1280 * n) : "memory");
        if (W_RB) {
          asm volatile("cp.async.bulk.commit_group;\ncp.async.bulk.wait_group.read 0;" ::: "memory");
          mbar_expect_tx(bars + 8 * B_WST, WO_BYTES / 2);
#pragma unroll 1
          for (int n = 0; n < 5; n++) bulk_load(sb + OFF_WS + 1280 * n, dst + 160 * n, 1280, bars + 8 * B_WST);
          mbar_wait(bars + 8 * B_WST, 1);
        } else {
          asm volatile("cp.async.bulk.commit_group;\ncp.async.bulk.wait_group 0;\nfence.proxy.async.global;" ::: "memory");
          if (!(NOMB & 4)) asm volatile("fence.release.gpu;" ::: "memory");
        }
        flag_bump(g_cnt + C_W + 32 * hg);
        mbar_arrive(bars + 8 * B_WOP);
        TS(71);
        mbar_expect_tx(bars + 8 * B_C34, 3 * U_BYTES);
        mbar_expect_tx(bars + 8 * B_YRB, 2 * U_BYTES);
#pragma unroll 1
        for (int c = 0; c < 5; c++) {
          mbar_wait(bars + 8 * (B_YST + c), 0);
          asm volatile("cp.async.bulk.global.shared::cta.bulk_group [%0], [%1], 4096;\ncp.async.bulk.commit_group;\n"
                       "cp.async.bulk.wait_group.read 0;" ::"l"(g_Y + (5 * b + c) * Y_PITCH), "r"(sb + off_ch(c)) : "memory");
          bulk_load(sb + off_ch(c), g_Y + (5 * b + c) * Y_PITCH, U_BYTES, bars + 8 * (c < 3 ? B_C34 : B_YRB));
        }
        TS(75);
        mbar_wait(bars + 8 * B_C34, 0);
        mbar_wait(bars + 8 * B_YRB, 0);
        flag_bump(g_cnt + C_Y + 32 * (b >> 4));
        TS(27);
        mbar_arrive(bars + 8 * B_YSIG);
        mbar_expect_tx(bars + 8 * B_YFULL, 20480);
        flag_wait(g_cnt + C_Y + 32 * hg, (lds32(sb + OFF_EPOCH) + 1) * 16);
        TS(24);
        tma_2d(sb + OFF_YT, &m.y, 128 * r, 80 * hg, bars + 8 * B_YFULL);
        tma_2d(sb + OFF_YT + 10240, &m.y, 128 * r + 64, 80 * hg, bars + 8 * B_YFULL);
      }
    }
  } else {
    asm volatile("setmaxnreg.inc.sync.aligned.u32 152;");
    if (wg < 2) {
      float acc[120];
#pragma unroll
      for (int i = 0; i < 120; i++) acc[i] = 0.f;
      const uint32_t da = desc_lo(sb + wg * 8192, 16), db = desc_lo(sb + ST_W, 8192), dc = desc_lo(sb + ST_WT, 2048);
      if (PW1) pin<120>(acc);
      if (PW1 == 2) mbar_wait(bars + 8 * B_FULL1, 0);
#pragma unroll 1
      for (int kb = 0; kb < 10; kb++) {
        mbar_wait(bars + 8 * (B_FULL1 + (kb & 3)), (kb >> 2) & 1);
        const uint32_t so = (kb & 3) * (STAGE_BYTES >> 4);
        wg_fence();
#pragma unroll
        for (int k = 0; k < 4; k++) {
          WgSST<192>::mma<HI_SW128, HI_SW128>(acc, da + so + 2 * k, db + so + 128 * k, 1);
          WgSST<48>::mma<HI_SW128, HI_SW32>(acc + 96, da + so + 2 * k, dc + so + 32 * k, 1);
        }
        wg_commit();
        wg_wait<1>();
        if (kb > 0 && lane == 0) mbar_arrive(bars + 8 * (kb == 4 ? B_E3 : B_EMPTY1 + ((kb - 1) & 3)));
      }
      mbar_wait(bars + 8 * B_EPOCH, 0);
      const uint32_t tag = lds32(sb + OFF_EPOCH) + 1;
      mbar_wait(bars + 8 * B_S3, 0);
      wg_wait<0>();
      pin<120>(acc);
      if (lane == 0) mbar_arrive(bars + 8 * B_P1);
      TSM(w == 0, 3 + wg);
      attention(acc, sb, b, wg, w, lane, tag, p.zero);
    } else {
      const int tw = tid & 127, chl = 64 * (b & 1) + 8 * w + (lane >> 2);
      uint4* up = g_U + chl * U_PITCH + ((4 * (b >> 1) + (lane & 3)) ^ ((b >> 2) & 1));
      uint2 sw[10];
      uint32_t dv = 0;
      if (lane < 5) dv = __ldg(reinterpret_cast<const unsigned short*>(p.ssm_D) + 5 * b + lane);
#pragma unroll
      for (int i = 0; i < 10; i++) sw[i] = ldg64(reinterpret_cast<const uint2*>(p.shift_k) + chl + 128 * (i >> 1) + 32 * (i & 1));
      uint32_t tab[12];
      uint32_t tt[2];
      fft_tables(tab, tw);
      fft_twiddles(tt, tw);
      uint4 res[10];
#pragma unroll
      for (int i = 0; i < 10; i++) res[i] = make_uint4(0, 0, 0, 0);
#pragma unroll 1
      for (int slab = 0; slab < 5; slab++) {
#pragma unroll
        for (int i = 0; i < 8; i++) res[i] = res[i + 2];
        prep_slab(res + 8, sw, sb, slab, w, lane);
        TSIF(w == 0, 99 + 4 * slab);
#pragma unroll
        for (int i = 0; i < 8; i++) sw[i] = sw[i + 2];
      }
      TSIF(w == 0, 28);
      __syncwarp();
      if (lane == 0) mbar_arrive(bars + 8 * B_KVD + ((res[8].x ^ res[9].x) & p.zero));
      mbar_wait(bars + 8 * B_KVD, 0);
      fft_tables_store(tab, sb, tw);
      mbar_wait(bars + 8 * B_LAST, 0);
#pragma unroll
      for (int i = 0; i < 10; i++) up[(128 * (i >> 1) + 32 * (i & 1)) * U_PITCH] = res[i];
      __syncwarp();
      if (lane == 0) mbar_arrive(bars + 8 * B_PREP);
      TSIF(w == 0 && !U_TMA, 5);
      mbar_wait(bars + 8 * (G_AFTER ? B_USIG : B_LAST), 0);
      prep_gate(p, sb, b, w, lane);
      __syncwarp();
      if (lane == 0) mbar_arrive(bars + 8 * B_GATE);
      TSIF(w == 0, 72);
      mbar_wait(bars + 8 * B_HB, 0);
      TSIF(w == 0, 2);
      const uint32_t ha = sb + U_BYTES + ((tw >> 3) * 16 + 8 + (tw & 7)) * 16;
      uint4 hv[5];
#pragma unroll
      for (int c = 0; c < 5; c++) hv[c] = lds128(ha + off_ch(c));
      __syncwarp();
#pragma unroll
      for (int c = 0; c < 5; c++) sts128((ha ^ 16) + off_ch(c), hv[c].x, hv[c].y, hv[c].z, hv[c].w);
      asm volatile("st.shared.v2.u32 [%0], {%1, %2};" ::"r"(sb + OFF_TT + 8 * tw), "r"(tt[0]), "r"(tt[1]) : "memory");
      if (tw < 5) asm volatile("st.shared.f32 [%0], %1;" ::"r"(sb + OFF_D + 4 * tw), "f"(bf_lo(dv) * 0.125f) : "memory");
      fence_async_smem();
      __syncwarp();
      if (lane == 0) mbar_arrive(bars + 8 * B_HA);
      TSIF(w == 0, 6);
    }

    FftConst fc;
    TSM(w == 0 && wg == 0, 104);
    mbar_wait(bars + 8 * B_HA, 0);
    fft_matrices(fc, sb, w, lane);
    TSM(w == 0 && wg == 0, 105);
    TSM(w == 0 && wg == 2, 124);
    uint32_t tasks = wg == 0 ? TASK0 : wg == 1 ? TASK1 : TASK2, fa[4][4];
    {
      float X[32];
      wg_fence();
      f_step(X, fc, desc_lo(sb + off_ch((tasks & 7) - 1) + U_BYTES, 1024));
      wg_wait<0>();
      pin<32>(X);
      twiddle_fwd(fa, X, fc);
    }
#pragma unroll 1
    for (; tasks; tasks >>= 4) {
      const int c = (tasks & 7) - 1;
      conv_channel(fc, fa, sb, c, ((tasks >> 4) & 7) - 1, wg, w, lane);
      if (lane == 0) mbar_arrive(bars + 8 * (B_YST + c));
      TSM(w == 0, 10 + c);
    }

    if (wg != WO_SKIP) {
      const int wg = (warp >> 2) > WO_SKIP ? (warp >> 2) - 1 : warp >> 2;
      const int g = lane >> 2;
      float acc[40];
#pragma unroll
      for (int i = 0; i < 40; i++) acc[i] = 0.f;
      const uint32_t da = desc_lo(sb + wg * 1024, 2048), db = desc_lo(sb, 2560);
      const int tr = 64 * wg + 16 * w + (lane & 15);
      const uint32_t fm = sb + OFF_QS + tr * 128, fx = (lane >> 4) ^ (tr & 7);
      const uint32_t ft = sb + OFF_QT + tr * 32 + (((lane >> 4) ^ (tr >> 2)) & 1) * 16;
      uint32_t qf[20];
      if (Q_REG) {
        mbar_wait(bars + 8 * B_QF, 0);
#pragma unroll
        for (int j = 0; j < 5; j++) ldsm4(qf + 4 * j, j < 4 ? fm + ((fx ^ (2 * j)) << 4) : ft);
        if (lane == 0) mbar_arrive(bars + 8 * B_QE + ((qf[3] ^ qf[7] ^ qf[11] ^ qf[15] ^ qf[19]) & p.zero));
      }
      mbar_wait(bars + 8 * B_ORB, 0);
      if (PW2) mbar_wait(bars + 8 * B_FULL2, 0);
      mbar_wait(bars + 8 * B_CVD, 0);
      TSM(w == 0, 15 + wg);
#pragma unroll 1
      for (int j = 0; j < 8; j++) {
        mbar_wait(bars + 8 * (B_FULL2 + j), 0);
        TSM(w == 0 && wg == 0, 44 + (j < 4 ? j : j + 6));
        const uint32_t oa = da + (off_o(j) >> 4), ob = db + (off_w(j) >> 4);
        wg_fence();
#pragma unroll
        for (int k = 0; k < 5; k++) WgSST<80>::mma<HI_NONE, HI_SW32>(acc, oa + 256 * k, ob + 32 * k, 1);
        wg_commit();
        wg_wait<1>();
        if (Q_REG == 2) {
          if ((j == 1 || j == 2 || j == 6) && lane == 0) mbar_arrive(bars + 8 * (B_EMPTY2 + (j == 6 ? 3 : j - 1)));
        } else if (j >= 1 && j <= Q_SLOT + 1 && lane == 0) {
          mbar_arrive(bars + 8 * (B_EMPTY2 + j - 1));
        }
      }
      TSIF(w == 0 && wg == 0, 113);
      const float g0 = __uint_as_float(lds32(sb + OFF_GATE + (64 * wg + 16 * w + g) * 4));
      const float g1 = __uint_as_float(lds32(sb + OFF_GATE + (64 * wg + 16 * w + 8 + g) * 4));
      const uint32_t ga = pack2(g0, g0), gb = pack2(g1, g1);
      const uint32_t na = pack2(1.f - g0, 1.f - g0), nb = pack2(1.f - g1, 1.f - g1);

      if (!Q_REG) {
        mbar_wait(bars + 8 * B_QF, 0);
#pragma unroll
        for (int j = 0; j < 5; j++) ldsm4(qf + 4 * j, j < 4 ? fm + ((fx ^ (2 * j)) << 4) : ft);
      } else {
        mbar_wait(bars + 8 * (B_EMPTY2 + 3), 0);
      }
      TSM(w == 0 && wg == 0, 99);
#pragma unroll
      for (int i = 0; i < 20; i++) {
        qf[i] = bmul((i & 1) ? gb : ga, qf[i]);
        asm volatile("" : "+r"(qf[i]));
      }

      wg_wait<0>();
      pin<40>(acc);
      TSM(w == 0, 17 + wg);
      uint32_t pb[20];
#pragma unroll
      for (int j = 0; j < 10; j++) {
        pb[2 * j] = bmul(na, pack2(acc[4 * j], acc[4 * j + 1]));
        pb[2 * j + 1] = bmul(nb, pack2(acc[4 * j + 2], acc[4 * j + 3]));
        asm volatile("" : "+r"(pb[2 * j]), "+r"(pb[2 * j + 1]));
      }
      const uint32_t ya = sb + OFF_YT + wg * 10240 + ((lane >> 4) * 8 + (lane & 7)) * 128 +
                          (((2 * w + (((lane >> 3) & 1) ^ wg)) ^ (lane & 7)) << 4);
      mbar_wait(bars + 8 * B_YFULL, 0);
      TSM(w == 0 && wg == 0, 19);
#pragma unroll
      for (int j = 0; j < 5; j++) {
        uint32_t y[4];
        ldsm4t(y, ya + 2048 * j);
#pragma unroll
        for (int i = 0; i < 4; i++)
          qf[4 * j + i] = bfma(qf[4 * j + i], y[i], pb[4 * j + i]);
      }
#pragma unroll
      for (int j = 0; j < 5; j++) stsm4(j < 4 ? fm + ((fx ^ (2 * j)) << 4) : ft, qf + 4 * j);
      fence_async_smem();
      __syncwarp();
      if (lane == 0) {
        const int row = 64 * wg + 16 * w;
        asm volatile("cp.async.bulk.tensor.2d.global.shared::cta.bulk_group [%0, {%2, %3}], [%1];"
                     ::"l"(&m.om), "r"(sb + OFF_QS + row * 128), "r"(80 * hg), "r"(128 * r + row) : "memory");
        asm volatile("cp.async.bulk.tensor.2d.global.shared::cta.bulk_group [%0, {%2, %3}], [%1];"
                     ::"l"(&m.ot), "r"(sb + OFF_QT + row * 32), "r"(80 * hg + 64), "r"(128 * r + row) : "memory");
        asm volatile("cp.async.bulk.commit_group;\ncp.async.bulk.wait_group.read 0;" ::: "memory");
      }
      TSM(w == 0 || w == 3, 40 + 2 * wg + (w & 1));
      if (ENDBAR) asm volatile("bar.sync 15, 256;" ::: "memory");
    }
  }
}

typedef CUresult (*EncodeFn)(CUtensorMap*, CUtensorMapDataType, cuuint32_t, void*, const cuuint64_t*, const cuuint64_t*,
                             const cuuint32_t*, const cuuint32_t*, CUtensorMapInterleave, CUtensorMapSwizzle,
                             CUtensorMapL2promotion, CUtensorMapFloatOOBfill);

void encode(EncodeFn fn, CUtensorMap* tm, const void* base, int rank, const cuuint64_t* dims, const cuuint64_t* strides,
            const cuuint32_t* box, CUtensorMapSwizzle swz) {
  const cuuint32_t ones[3] = {1, 1, 1};
  fn(tm, CU_TENSOR_MAP_DATA_TYPE_BFLOAT16, rank, const_cast<void*>(base), dims, strides, box, ones,
     CU_TENSOR_MAP_INTERLEAVE_NONE, swz, CU_TENSOR_MAP_L2_PROMOTION_L2_128B, CU_TENSOR_MAP_FLOAT_OOB_FILL_NONE);
}

}

extern "C" void kernel_launch(void* const* d_in, const int* in_sizes, int n_in, void* d_out, int out_size) {
  (void)in_sizes; (void)n_in; (void)out_size;
  Params p;
  p.q = (const __nv_bfloat16*)d_in[0];
  p.k = (const __nv_bfloat16*)d_in[1];
  p.v = (const __nv_bfloat16*)d_in[2];
  p.shift_k = (const __nv_bfloat16*)d_in[3];
  p.ssm_k = (const __nv_bfloat16*)d_in[4];
  p.ssm_D = (const __nv_bfloat16*)d_in[5];
  p.wqkv = (const __nv_bfloat16*)d_in[7];
  p.wo = (const __nv_bfloat16*)d_in[8];
  p.gate_w = (const __nv_bfloat16*)d_in[9];
  p.out = (__nv_bfloat16*)d_out;
  p.zero = 0;

  static EncodeFn fn = nullptr;
  static void *yaddr = nullptr, *uaddr = nullptr;
  if (!fn) {
    cudaDriverEntryPointQueryResult qr;
    void* f = nullptr;
    cudaGetDriverEntryPoint("cuTensorMapEncodeTiled", &f, cudaEnableDefault, &qr);
    fn = (EncodeFn)f;
    cudaGetSymbolAddress(&yaddr, g_Y);
    cudaGetSymbolAddress(&uaddr, g_U);
    cudaFuncSetAttribute(fused_kernel, cudaFuncAttributeMaxDynamicSharedMemorySize, SMEM_BYTES);
  }
  Maps m;
  {
    const cuuint64_t dims[3] = {640, 1024, 2}, st[2] = {2560, 1280};
    const cuuint32_t box[3] = {64, 64, 2};
    encode(fn, &m.x, p.q, 3, dims, st, box, CU_TENSOR_MAP_SWIZZLE_128B);
  }
  {
    const cuuint64_t dims[3] = {640, 640, 3}, st[2] = {3840, 1280};
    const cuuint32_t box[3] = {64, 64, 3}, boxt[3] = {16, 64, 3};
    encode(fn, &m.wm, p.wqkv, 3, dims, st, box, CU_TENSOR_MAP_SWIZZLE_128B);
    encode(fn, &m.wt, p.wqkv, 3, dims, st, boxt, CU_TENSOR_MAP_SWIZZLE_32B);
  }
  {
    const cuuint64_t dims[3] = {64, 2048, 10}, st[2] = {1280, 128};
    const cuuint32_t boxk[3] = {64, 35, 1}, boxv[3] = {64, 32, 1};
    encode(fn, &m.k, p.k, 3, dims, st, boxk, CU_TENSOR_MAP_SWIZZLE_128B);
    encode(fn, &m.v, p.v, 3, dims, st, boxv, CU_TENSOR_MAP_SWIZZLE_128B);
  }
  {
    const cuuint64_t dims[3] = {16, 640, 40}, st[2] = {1280, 32};
    const cuuint32_t box[3] = {16, 40, 5};
    encode(fn, &m.wo, p.wo, 3, dims, st, box, CU_TENSOR_MAP_SWIZZLE_32B);
  }
  {
    const cuuint64_t dims[2] = {2048, 640}, st[1] = {Y_PITCH * 16};
    const cuuint32_t box[2] = {64, 80};
    encode(fn, &m.y, yaddr, 2, dims, st, box, CU_TENSOR_MAP_SWIZZLE_128B);
    const cuuint64_t stu[1] = {U_PITCH * 16};
    const cuuint32_t boxu[2] = {32, 64};
    encode(fn, &m.u, uaddr, 2, dims, stu, boxu, CU_TENSOR_MAP_SWIZZLE_NONE);
  }
  {
    const cuuint64_t dims[2] = {640, 2048}, st[1] = {1280};
    const cuuint32_t bqm[2] = {64, 128}, bqt[2] = {16, 128}, bom[2] = {64, 16}, bot[2] = {16, 16};
    encode(fn, &m.qm, p.q, 2, dims, st, bqm, CU_TENSOR_MAP_SWIZZLE_128B);
    encode(fn, &m.qt, p.q, 2, dims, st, bqt, CU_TENSOR_MAP_SWIZZLE_32B);
    encode(fn, &m.om, p.out, 2, dims, st, bom, CU_TENSOR_MAP_SWIZZLE_128B);
    encode(fn, &m.ot, p.out, 2, dims, st, bot, CU_TENSOR_MAP_SWIZZLE_32B);
  }
  fused_kernel<<<NCTA, NTHR, SMEM_BYTES>>>(m, p);
}
```

```cpp
#include <cuda.h>
#include <cuda_bf16.h>
#include <cuda_runtime.h>
#include <stdint.h>

namespace {

constexpr int SEQ = 2048, DIM = 640, NCTA = 128, NTHR = 512;

#define TRIG_KB 9
#define KV_KB 2
#define DEV_EXIT 0
#define ATT_GATE 0
#define G_AFTER 0
#define FENCE_LO 0
#define FENCE_HI 0
#define PW1 2
#define PW2 1
#define ENDBAR 0
#define PAD_KB 0
#define Y_ALIAS 1
#define NOMB 0
#define SRC_ROT 0
#define WAIT_NS 0
#define WB_TRIG B_USIG
#define G_POS 0
#define TAILF 1
#define T_ISSUE 384
#define T_PF 416
#define T_INIT 448
#define ATT_MERGE 0
#define BMAP 1
#define PRE2 1
#define KV_MIX 0
#define O_DEFER 0
#define TASK0 0x3
#define TASK1 0x52
#define TASK2 0x41
#define HALO_FIRST 1
#define PREV_EARLY 0
#define Y_RB 2
#define O_RB 2
#define O_EAGER 1
#define OP_TRIG B_ATTN
#define FUSE_MIX 1
#define Q_EARLY 1
#define U_TRIM 1
#define Q_SLOT 3
#define G_TMA 1
#define W_RB 1
#define WPF B_S3
#define WPF_LIN 1
#define QBOX 0
#define ACQ 0
#define U_TMA 0
#define U_GATE 0
#define RF_GATE 0
#define WO_TRIG B_WST
#define WL_TRIG B_WOP
#define WO_GATE 4

constexpr uint32_t STAGE_BYTES = 47104, ST_W = 16384, ST_WT = 40960;
constexpr uint32_t O_BYTES = 20480, WO_BYTES = 12800;
constexpr uint32_t OFF_OA = 0;
constexpr uint32_t OFF_QS = Q_SLOT * O_BYTES, OFF_QT = OFF_QS + 16384;
constexpr uint32_t OFF_WC = 81920;
constexpr uint32_t OFF_WA = 94720;
constexpr uint32_t OFF_GATE = 145920;
constexpr uint32_t OFF_TT = 146432;
constexpr uint32_t OFF_KVX = 148480;
constexpr uint32_t OFF_CH3 = 163840;
constexpr uint32_t CH_BYTES = 12288, U_BYTES = 4096;
constexpr uint32_t OFF_FT = 225280, OFF_GT = 229376;
constexpr uint32_t OFF_CH0 = 188416;
constexpr uint32_t OFF_KVS = OFF_CH0, KVS_V = 4480, KVS_BYTES = 8576;
constexpr uint32_t OFF_WS = OFF_WA;
__device__ __forceinline__ uint32_t off_us(int s) { return OFF_CH0 + 4096 * ((0x65320 >> (4 * s)) & 7); }
constexpr uint32_t OFF_YT = 163840;
constexpr uint32_t OFF_BAR = 231936;
constexpr uint32_t SMEM_BYTES = OFF_BAR + 512;

enum : uint32_t {
  B_FULL1 = 0, B_EMPTY1 = 4, B_S3 = 7, B_FULL2 = 52, B_EMPTY2 = 13, B_U = 8, B_GATE = 12, B_HA = 19, B_HB = 20,
  B_ATTN = 21, B_C34 = 22, B_YRB = 23, B_YFULL = 24, B_EPOCH = 25, B_PREP = 26, B_P1 = 27, B_LAST = 28,
  B_E3 = 29, B_OSIG = 30, B_WOP = 31, B_USIG = 32, B_WST = 33, B_KV = 34, B_KVD = 39, B_QF = 17, B_ATT2 = 18, B_YST = 40,
  B_ORB = 45, B_CVD = 33 + 14, B_US = 45, B_YSIG = 50
};
constexpr uint32_t OFF_EPOCH = OFF_BAR + 8 * 51, OFF_D = OFF_BAR + 8 * 60;
__device__ __forceinline__ uint32_t off_o(int j) { return j < 4 ? OFF_OA + j * O_BYTES : j < 6 ? OFF_CH0 + (j - 4) * O_BYTES : OFF_OA + (j - 6) * O_BYTES; }
__device__ __forceinline__ uint32_t off_w(int j) { return j < 4 ? OFF_WA + j * WO_BYTES : j == 4 ? OFF_KVX : j == 5 ? OFF_WC : OFF_WA + (j - 6) * WO_BYTES; }
__device__ __forceinline__ int step_src(int hg, int j) {
  if (SRC_ROT == 2) {
    const int pos = (0x37621540 >> (4 * hg)) & 7;
    return j == 0 ? hg : (0x65217430 >> (4 * (j <= pos ? j - 1 : j))) & 7;
  }
  return SRC_ROT ? (hg + j) & 7 : j == 0 ? hg : j <= hg ? j - 1 : j;
}
__device__ __forceinline__ bool tail_first(int hg) { return TAILF && (hg & 3) == 3; }
__device__ __forceinline__ uint32_t off_ch(int c) { return (c < 3 ? OFF_CH0 : OFF_CH3 - 3 * CH_BYTES) + c * CH_BYTES; }

#define U_PITCH 264
__device__ __align__(1024) uint4 g_U[DIM * U_PITCH];
__device__ uint4 g_O[NCTA * 1280];
#define g_Y g_U
constexpr int Y_PITCH = U_PITCH;
__device__ uint4 g_WO[64 * 800];
__device__ uint4 g_halo[NCTA * 2 * 7 * 32];
__device__ __align__(128) float g_gate[SEQ + PAD_KB * 256];
__device__ unsigned g_cnt[32 * (1 + 2 * 16 + 8 + NCTA)];
constexpr int C_LAUNCH = 0, C_PREP = 32, C_Y = 32 * 17, C_W = 32 * 33, C_O = 32 * 41;

#define TSM(cond, slot) do { } while (0)
#define TSIF(cond, slot) do { if (__LINE__ >= FENCE_LO && __LINE__ < FENCE_HI) sched_fence(); } while (0)
__device__ __forceinline__ void sched_fence() {
  asm volatile("{\n.reg .pred p;\n.reg .u32 c;\nmov.u32 c, %%clock;\nsetp.eq.u32 p, c, 0;\n@p st.shared.u32 [%0], c;\n}"
               ::"r"(1024 + OFF_EPOCH + 4) : "memory");
}
#define TS(slot) TSIF(true, slot)

struct Params {
  const __nv_bfloat16 *q, *k, *v, *shift_k, *ssm_k, *ssm_D, *wqkv, *wo, *gate_w;
  __nv_bfloat16* out;
  uint32_t zero;
};

#define POLL_NS 0
constexpr int SPIN_LIMIT = 1 << 17;

__device__ __forceinline__ void mbar_init(uint32_t bar, uint32_t count) {
  asm volatile("mbarrier.init.shared::cta.b64 [%0], %1;" ::"r"(bar), "r"(count) : "memory");
}
__device__ __forceinline__ void mbar_expect_tx(uint32_t bar, uint32_t bytes) {
  asm volatile("mbarrier.arrive.expect_tx.shared::cta.b64 _, [%0], %1;" ::"r"(bar), "r"(bytes) : "memory");
}
__device__ __forceinline__ void mbar_arrive(uint32_t bar) {
  asm volatile("mbarrier.arrive.shared::cta.b64 _, [%0];" ::"r"(bar) : "memory");
}
__device__ __forceinline__ void mbar_wait(uint32_t bar, uint32_t parity) {
  uint32_t ok;
  int spins = 0;
  do {
    if (WAIT_NS)
      asm volatile("{\n.reg .pred p;\nmbarrier.try_wait.parity.shared::cta.b64 p, [%1], %2, %3;\nselp.b32 %0, 1, 0, p;\n}"
                   : "=r"(ok) : "r"(bar), "r"(parity), "r"(WAIT_NS) : "memory");
    else
      asm volatile("{\n.reg .pred p;\nmbarrier.try_wait.parity.shared::cta.b64 p, [%1], %2;\nselp.b32 %0, 1, 0, p;\n}"
                   : "=r"(ok) : "r"(bar), "r"(parity) : "memory");
    if (++spins > SPIN_LIMIT) break;
  } while (!ok);
}
__device__ __forceinline__ unsigned flag_read(const unsigned* p) {
  unsigned v;
  asm volatile("ld.relaxed.gpu.global.u32 %0, [%1];" : "=r"(v) : "l"(p) : "memory");
  return v;
}
__device__ __forceinline__ void flag_poll(const unsigned* p, unsigned target) {
  unsigned v;
  int spins = 0;
  do {
    if (POLL_NS && spins) __nanosleep(POLL_NS);
    asm volatile("ld.relaxed.gpu.global.u32 %0, [%1];" : "=r"(v) : "l"(p) : "memory");
    if (++spins > SPIN_LIMIT) break;
  } while ((int)(v - target) < 0);
}
__device__ __forceinline__ void flag_wait(const unsigned* p, unsigned target) {
  flag_poll(p, target);
  if (ACQ) asm volatile("fence.acquire.gpu;\nfence.proxy.async.global;" ::: "memory");
}
__device__ __forceinline__ void flag_signal(unsigned* p, int n, int lane) {
  if (lane == 0) asm volatile("fence.release.gpu;" ::: "memory");
  __syncwarp();
  if (lane < n) asm volatile("red.relaxed.gpu.global.add.u32 [%0], 1;" ::"l"(p + 32 * lane) : "memory");
}
__device__ __forceinline__ void flag_bump(unsigned* p) {
  asm volatile("red.relaxed.gpu.global.add.u32 [%0], 1;" ::"l"(p) : "memory");
}
__device__ __forceinline__ void fence_async_smem() { asm volatile("fence.proxy.async.shared::cta;" ::: "memory"); }
__device__ __forceinline__ void wg_sync(int id) { asm volatile("bar.sync %0, 128;" ::"r"(id) : "memory"); }

__device__ __forceinline__ void tma_2d(uint32_t dst, const CUtensorMap* tm, int c0, int c1, uint32_t bar) {
  asm volatile("cp.async.bulk.tensor.2d.shared::cluster.global.mbarrier::complete_tx::bytes [%0], [%1, {%3, %4}], [%2];"
               ::"r"(dst), "l"(tm), "r"(bar), "r"(c0), "r"(c1) : "memory");
}
__device__ __forceinline__ void tma_3d(uint32_t dst, const CUtensorMap* tm, int c0, int c1, int c2, uint32_t bar) {
  asm volatile("cp.async.bulk.tensor.3d.shared::cluster.global.mbarrier::complete_tx::bytes [%0], [%1, {%3, %4, %5}], [%2];"
               ::"r"(dst), "l"(tm), "r"(bar), "r"(c0), "r"(c1), "r"(c2) : "memory");
}
__device__ __forceinline__ void bulk_load(uint32_t dst, const void* src, uint32_t bytes, uint32_t bar) {
  asm volatile("cp.async.bulk.shared::cluster.global.mbarrier::complete_tx::bytes [%0], [%1], %2, [%3];"
               ::"r"(dst), "l"(src), "r"(bytes), "r"(bar) : "memory");
}
__device__ __forceinline__ void tm_prefetch(const CUtensorMap* tm) {
  asm volatile("prefetch.tensormap [%0];" ::"l"(tm) : "memory");
}

__device__ __forceinline__ void wg_fence() { asm volatile("wgmma.fence.sync.aligned;" ::: "memory"); }
__device__ __forceinline__ void wg_commit() { asm volatile("wgmma.commit_group.sync.aligned;" ::: "memory"); }
template <int N> __device__ __forceinline__ void wg_wait() { asm volatile("wgmma.wait_group.sync.aligned %0;" ::"n"(N) : "memory"); }
__device__ __forceinline__ uint32_t desc_lo(uint32_t addr, uint32_t lbo) { return ((addr & 0x3FFFF) >> 4) | ((lbo >> 4) << 16); }
constexpr uint32_t desc_hi(uint32_t sbo, uint32_t swz) { return (sbo >> 4) | (swz << 30); }
constexpr uint32_t HI_SW128 = desc_hi(1024, 1), HI_SW64 = desc_hi(512, 2), HI_SW32 = desc_hi(256, 3), HI_NONE = desc_hi(128, 0);
template <int N> __device__ __forceinline__ void pin(float* d) {
#pragma unroll
  for (int i = 0; i < N; i++) asm volatile("" : "+f"(d[i])::"memory");
}

__device__ __forceinline__ uint32_t lds32(uint32_t a) {
  uint32_t v;
  asm volatile("ld.volatile.shared.u32 %0, [%1];" : "=r"(v) : "r"(a) : "memory");
  return v;
}
__device__ __forceinline__ uint4 ldg128(const void* a) {
  uint4 v;
  asm volatile("ld.global.nc.v4.u32 {%0, %1, %2, %3}, [%4];" : "=r"(v.x), "=r"(v.y), "=r"(v.z), "=r"(v.w) : "l"(a) : "memory");
  return v;
}
__device__ __forceinline__ uint2 ldg64(const void* a) {
  uint2 v;
  asm volatile("ld.global.nc.v2.u32 {%0, %1}, [%2];" : "=r"(v.x), "=r"(v.y) : "l"(a) : "memory");
  return v;
}
__device__ __forceinline__ void ldsm4(uint32_t* r, uint32_t a) {
  asm volatile("ldmatrix.sync.aligned.m8n8.x4.shared.b16 {%0, %1, %2, %3}, [%4];"
               : "=r"(r[0]), "=r"(r[1]), "=r"(r[2]), "=r"(r[3]) : "r"(a) : "memory");
}
__device__ __forceinline__ void ldsm4t(uint32_t* r, uint32_t a) {
  asm volatile("ldmatrix.sync.aligned.m8n8.x4.trans.shared.b16 {%0, %1, %2, %3}, [%4];"
               : "=r"(r[0]), "=r"(r[1]), "=r"(r[2]), "=r"(r[3]) : "r"(a) : "memory");
}
__device__ __forceinline__ uint2 lds64(uint32_t a) {
  uint2 v;
  asm volatile("ld.shared.v2.u32 {%0, %1}, [%2];" : "=r"(v.x), "=r"(v.y) : "r"(a) : "memory");
  return v;
}
__device__ __forceinline__ uint4 lds128(uint32_t a) {
  uint4 v;
  asm volatile("ld.shared.v4.u32 {%0, %1, %2, %3}, [%4];" : "=r"(v.x), "=r"(v.y), "=r"(v.z), "=r"(v.w) : "r"(a) : "memory");
  return v;
}
__device__ __forceinline__ void sts128(uint32_t a, uint32_t x, uint32_t y, uint32_t z, uint32_t w) {
  asm volatile("st.shared.v4.u32 [%0], {%1, %2, %3, %4};" ::"r"(a), "r"(x), "r"(y), "r"(z), "r"(w) : "memory");
}
__device__ __forceinline__ void stsm4(uint32_t a, const uint32_t* r) {
  asm volatile("stmatrix.sync.aligned.m8n8.x4.shared.b16 [%0], {%1, %2, %3, %4};" ::"r"(a), "r"(r[0]), "r"(r[1]), "r"(r[2]), "r"(r[3]) : "memory");
}
__device__ __forceinline__ void stsm4t(uint32_t a, const uint32_t* r) {
  asm volatile("stmatrix.sync.aligned.m8n8.x4.trans.shared.b16 [%0], {%1, %2, %3, %4};" ::"r"(a), "r"(r[0]), "r"(r[1]), "r"(r[2]), "r"(r[3]) : "memory");
}
__device__ __forceinline__ uint32_t pack2(float lo, float hi) {
  uint32_t r;
  asm("cvt.rn.bf16x2.f32 %0, %1, %2;" : "=r"(r) : "f"(hi), "f"(lo));
  return r;
}
__device__ __forceinline__ uint32_t movm(uint32_t a) {
  uint32_t d;
  asm volatile("movmatrix.sync.aligned.m8n8.trans.b16 %0, %1;" : "=r"(d) : "r"(a));
  return d;
}
__device__ __forceinline__ uint32_t bmul(uint32_t a, uint32_t b) {
  uint32_t d;
  asm("mul.rn.bf16x2 %0, %1, %2;" : "=r"(d) : "r"(a), "r"(b));
  return d;
}
__device__ __forceinline__ uint32_t badd(uint32_t a, uint32_t b) {
  uint32_t d;
  asm("add.rn.bf16x2 %0, %1, %2;" : "=r"(d) : "r"(a), "r"(b));
  return d;
}
__device__ __forceinline__ uint32_t bfma(uint32_t a, uint32_t b, uint32_t c) {
  uint32_t d;
  asm("fma.rn.bf16x2 %0, %1, %2, %3;" : "=r"(d) : "r"(a), "r"(b), "r"(c));
  return d;
}
__device__ __forceinline__ float bf_lo(uint32_t x) { return __uint_as_float(x << 16); }
__device__ __forceinline__ float bf_hi(uint32_t x) { return __uint_as_float(x & 0xFFFF0000u); }
__device__ __forceinline__ float ex2(float x) {
  float y;
  asm("ex2.approx.ftz.f32 %0, %1;" : "=f"(y) : "f"(x));
  return y;
}
__device__ __forceinline__ float rcp(float x) {
  float y;
  asm("rcp.approx.ftz.f32 %0, %1;" : "=f"(y) : "f"(x));
  return y;
}
__device__ __forceinline__ void mma16816(float* d, uint32_t a0, uint32_t a1, uint32_t a2, uint32_t a3, uint32_t b0, uint32_t b1) {
  asm volatile("mma.sync.aligned.m16n8k16.row.col.f32.bf16.bf16.f32 {%0, %1, %2, %3}, {%4, %5, %6, %7}, {%8, %9}, {%0, %1, %2, %3};"
               : "+f"(d[0]), "+f"(d[1]), "+f"(d[2]), "+f"(d[3])
               : "r"(a0), "r"(a1), "r"(a2), "r"(a3), "r"(b0), "r"(b1));
}
__device__ __forceinline__ void mma1688(float* d, uint32_t a0, uint32_t a1, uint32_t b0) {
  asm volatile("mma.sync.aligned.m16n8k8.row.col.f32.bf16.bf16.f32 {%0, %1, %2, %3}, {%4, %5}, {%6}, {%0, %1, %2, %3};"
               : "+f"(d[0]), "+f"(d[1]), "+f"(d[2]), "+f"(d[3])
               : "r"(a0), "r"(a1), "r"(b0));
}

template <int N> struct WgRS;
template <int N> struct WgSST;
template <> struct WgRS<32> {
  template <uint32_t HB>
  static __device__ __forceinline__ void mma(float* d, const uint32_t* a, uint32_t db) {
    asm volatile("{\n.reg .pred p;\n.reg .b64 db;\nsetp.ne.b32 p, %22, 0;\n"
      "mov.b64 db, {%20, %21};\n"
      "wgmma.mma_async.sync.aligned.m64n32k16.f32.bf16.bf16 {"
      "%0, %1, %2, %3, %4, %5, %6, %7, %8, %9, %10, %11, %12, %13, %14, %15"
      "}, {%16, %17, %18, %19}, db, p, 1, 1, 1;\n}\n"
      : "+f"(d[0]), "+f"(d[1]), "+f"(d[2]), "+f"(d[3]), "+f"(d[4]), "+f"(d[5]), "+f"(d[6]), "+f"(d[7]),
        "+f"(d[8]), "+f"(d[9]), "+f"(d[10]), "+f"(d[11]), "+f"(d[12]), "+f"(d[13]), "+f"(d[14]), "+f"(d[15])
      : "r"(a[0]), "r"(a[1]), "r"(a[2]), "r"(a[3]), "r"(db), "n"(HB), "n"(1));
  }
  template <uint32_t HB>
  static __device__ __forceinline__ void set(float* d, const uint32_t* a, uint32_t db) {
    asm volatile("{\n.reg .pred p;\n.reg .b64 db;\nsetp.ne.b32 p, %22, 0;\n"
      "mov.b64 db, {%20, %21};\n"
      "wgmma.mma_async.sync.aligned.m64n32k16.f32.bf16.bf16 {"
      "%0, %1, %2, %3, %4, %5, %6, %7, %8, %9, %10, %11, %12, %13, %14, %15"
      "}, {%16, %17, %18, %19}, db, p, 1, 1, 1;\n}\n"
      : "=f"(d[0]), "=f"(d[1]), "=f"(d[2]), "=f"(d[3]), "=f"(d[4]), "=f"(d[5]), "=f"(d[6]), "=f"(d[7]),
        "=f"(d[8]), "=f"(d[9]), "=f"(d[10]), "=f"(d[11]), "=f"(d[12]), "=f"(d[13]), "=f"(d[14]), "=f"(d[15])
      : "r"(a[0]), "r"(a[1]), "r"(a[2]), "r"(a[3]), "r"(db), "n"(HB), "n"(0));
  }
};
template <> struct WgRS<64> {
  template <uint32_t HB>
  static __device__ __forceinline__ void mma(float* d, const uint32_t* a, uint32_t db) {
    asm volatile("{\n.reg .pred p;\n.reg .b64 db;\nsetp.ne.b32 p, %38, 0;\n"
      "mov.b64 db, {%36, %37};\n"
      "wgmma.mma_async.sync.aligned.m64n64k16.f32.bf16.bf16 {"
      "%0, %1, %2, %3, %4, %5, %6, %7, %8, %9, %10, %11, %12, %13, %14, %15, "
      "%16, %17, %18, %19, %20, %21, %22, %23, %24, %25, %26, %27, %28, %29, %30, %31"
      "}, {%32, %33, %34, %35}, db, p, 1, 1, 1;\n}\n"
      : "+f"(d[0]), "+f"(d[1]), "+f"(d[2]), "+f"(d[3]), "+f"(d[4]), "+f"(d[5]), "+f"(d[6]), "+f"(d[7]),
        "+f"(d[8]), "+f"(d[9]), "+f"(d[10]), "+f"(d[11]), "+f"(d[12]), "+f"(d[13]), "+f"(d[14]), "+f"(d[15]),
        "+f"(d[16]), "+f"(d[17]), "+f"(d[18]), "+f"(d[19]), "+f"(d[20]), "+f"(d[21]), "+f"(d[22]), "+f"(d[23]),
        "+f"(d[24]), "+f"(d[25]), "+f"(d[26]), "+f"(d[27]), "+f"(d[28]), "+f"(d[29]), "+f"(d[30]), "+f"(d[31])
      : "r"(a[0]), "r"(a[1]), "r"(a[2]), "r"(a[3]), "r"(db), "n"(HB), "n"(1));
  }
  template <uint32_t HB>
  static __device__ __forceinline__ void set(float* d, const uint32_t* a, uint32_t db) {
    asm volatile("{\n.reg .pred p;\n.reg .b64 db;\nsetp.ne.b32 p, %38, 0;\n"
      "mov.b64 db, {%36, %37};\n"
      "wgmma.mma_async.sync.aligned.m64n64k16.f32.bf16.bf16 {"
      "%0, %1, %2, %3, %4, %5, %6, %7, %8, %9, %10, %11, %12, %13, %14, %15, "
      "%16, %17, %18, %19, %20, %21, %22, %23, %24, %25, %26, %27, %28, %29, %30, %31"
      "}, {%32, %33, %34, %35}, db, p, 1, 1, 1;\n}\n"
      : "=f"(d[0]), "=f"(d[1]), "=f"(d[2]), "=f"(d[3]), "=f"(d[4]), "=f"(d[5]), "=f"(d[6]), "=f"(d[7]),
        "=f"(d[8]), "=f"(d[9]), "=f"(d[10]), "=f"(d[11]), "=f"(d[12]), "=f"(d[13]), "=f"(d[14]), "=f"(d[15]),
        "=f"(d[16]), "=f"(d[17]), "=f"(d[18]), "=f"(d[19]), "=f"(d[20]), "=f"(d[21]), "=f"(d[22]), "=f"(d[23]),
        "=f"(d[24]), "=f"(d[25]), "=f"(d[26]), "=f"(d[27]), "=f"(d[28]), "=f"(d[29]), "=f"(d[30]), "=f"(d[31])
      : "r"(a[0]), "r"(a[1]), "r"(a[2]), "r"(a[3]), "r"(db), "n"(HB), "n"(0));
  }
};
template <> struct WgSST<48> {
  template <uint32_t HA, uint32_t HB>
  static __device__ __forceinline__ void mma(float* d, uint32_t da, uint32_t db, int sc) {
    asm volatile("{\n.reg .pred p;\n.reg .b64 da, db;\nsetp.ne.b32 p, %28, 0;\n"
      "mov.b64 da, {%24, %25};\nmov.b64 db, {%26, %27};\n"
      "wgmma.mma_async.sync.aligned.m64n48k16.f32.bf16.bf16 {"
      "%0, %1, %2, %3, %4, %5, %6, %7, %8, %9, %10, %11, %12, %13, %14, %15, "
      "%16, %17, %18, %19, %20, %21, %22, %23"
      "}, da, db, p, 1, 1, 0, 1;\n}\n"
      : "+f"(d[0]), "+f"(d[1]), "+f"(d[2]), "+f"(d[3]), "+f"(d[4]), "+f"(d[5]), "+f"(d[6]), "+f"(d[7]),
        "+f"(d[8]), "+f"(d[9]), "+f"(d[10]), "+f"(d[11]), "+f"(d[12]), "+f"(d[13]), "+f"(d[14]), "+f"(d[15]),
        "+f"(d[16]), "+f"(d[17]), "+f"(d[18]), "+f"(d[19]), "+f"(d[20]), "+f"(d[21]), "+f"(d[22]), "+f"(d[23])
      : "r"(da), "n"(HA), "r"(db), "n"(HB), "r"(sc));
  }
};
template <> struct WgSST<80> {
  template <uint32_t HA, uint32_t HB>
  static __device__ __forceinline__ void mma(float* d, uint32_t da, uint32_t db, int sc) {
    asm volatile("{\n.reg .pred p;\n.reg .b64 da, db;\nsetp.ne.b32 p, %44, 0;\n"
      "mov.b64 da, {%40, %41};\nmov.b64 db, {%42, %43};\n"
      "wgmma.mma_async.sync.aligned.m64n80k16.f32.bf16.bf16 {"
      "%0, %1, %2, %3, %4, %5, %6, %7, %8, %9, %10, %11, %12, %13, %14, %15, "
      "%16, %17, %18, %19, %20, %21, %22, %23, %24, %25, %26, %27, %28, %29, %30, %31, "
      "%32, %33, %34, %35, %36, %37, %38, %39"
      "}, da, db, p, 1, 1, 0, 1;\n}\n"
      : "+f"(d[0]), "+f"(d[1]), "+f"(d[2]), "+f"(d[3]), "+f"(d[4]), "+f"(d[5]), "+f"(d[6]), "+f"(d[7]),
        "+f"(d[8]), "+f"(d[9]), "+f"(d[10]), "+f"(d[11]), "+f"(d[12]), "+f"(d[13]), "+f"(d[14]), "+f"(d[15]),
        "+f"(d[16]), "+f"(d[17]), "+f"(d[18]), "+f"(d[19]), "+f"(d[20]), "+f"(d[21]), "+f"(d[22]), "+f"(d[23]),
        "+f"(d[24]), "+f"(d[25]), "+f"(d[26]), "+f"(d[27]), "+f"(d[28]), "+f"(d[29]), "+f"(d[30]), "+f"(d[31]),
        "+f"(d[32]), "+f"(d[33]), "+f"(d[34]), "+f"(d[35]), "+f"(d[36]), "+f"(d[37]), "+f"(d[38]), "+f"(d[39])
      : "r"(da), "n"(HA), "r"(db), "n"(HB), "r"(sc));
  }
};
template <> struct WgSST<192> {
  template <uint32_t HA, uint32_t HB>
  static __device__ __forceinline__ void mma(float* d, uint32_t da, uint32_t db, int sc) {
    asm volatile("{\n.reg .pred p;\n.reg .b64 da, db;\nsetp.ne.b32 p, %100, 0;\n"
      "mov.b64 da, {%96, %97};\nmov.b64 db, {%98, %99};\n"
      "wgmma.mma_async.sync.aligned.m64n192k16.f32.bf16.bf16 {"
      "%0, %1, %2, %3, %4, %5, %6, %7, %8, %9, %10, %11, %12, %13, %14, %15, "
      "%16, %17, %18, %19, %20, %21, %22, %23, %24, %25, %26, %27, %28, %29, %30, %31, "
      "%32, %33, %34, %35, %36, %37, %38, %39, %40, %41, %42, %43, %44, %45, %46, %47, "
      "%48, %49, %50, %51, %52, %53, %54, %55, %56, %57, %58, %59, %60, %61, %62, %63, "
      "%64, %65, %66, %67, %68, %69, %70, %71, %72, %73, %74, %75, %76, %77, %78, %79, "
      "%80, %81, %82, %83, %84, %85, %86, %87, %88, %89, %90, %91, %92, %93, %94, %95"
      "}, da, db, p, 1, 1, 0, 1;\n}\n"
      : "+f"(d[0]), "+f"(d[1]), "+f"(d[2]), "+f"(d[3]), "+f"(d[4]), "+f"(d[5]), "+f"(d[6]), "+f"(d[7]),
        "+f"(d[8]), "+f"(d[9]), "+f"(d[10]), "+f"(d[11]), "+f"(d[12]), "+f"(d[13]), "+f"(d[14]), "+f"(d[15]),
        "+f"(d[16]), "+f"(d[17]), "+f"(d[18]), "+f"(d[19]), "+f"(d[20]), "+f"(d[21]), "+f"(d[22]), "+f"(d[23]),
        "+f"(d[24]), "+f"(d[25]), "+f"(d[26]), "+f"(d[27]), "+f"(d[28]), "+f"(d[29]), "+f"(d[30]), "+f"(d[31]),
        "+f"(d[32]), "+f"(d[33]), "+f"(d[34]), "+f"(d[35]), "+f"(d[36]), "+f"(d[37]), "+f"(d[38]), "+f"(d[39]),
        "+f"(d[40]), "+f"(d[41]), "+f"(d[42]), "+f"(d[43]), "+f"(d[44]), "+f"(d[45]), "+f"(d[46]), "+f"(d[47]),
        "+f"(d[48]), "+f"(d[49]), "+f"(d[50]), "+f"(d[51]), "+f"(d[52]), "+f"(d[53]), "+f"(d[54]), "+f"(d[55]),
        "+f"(d[56]), "+f"(d[57]), "+f"(d[58]), "+f"(d[59]), "+f"(d[60]), "+f"(d[61]), "+f"(d[62]), "+f"(d[63]),
        "+f"(d[64]), "+f"(d[65]), "+f"(d[66]), "+f"(d[67]), "+f"(d[68]), "+f"(d[69]), "+f"(d[70]), "+f"(d[71]),
        "+f"(d[72]), "+f"(d[73]), "+f"(d[74]), "+f"(d[75]), "+f"(d[76]), "+f"(d[77]), "+f"(d[78]), "+f"(d[79]),
        "+f"(d[80]), "+f"(d[81]), "+f"(d[82]), "+f"(d[83]), "+f"(d[84]), "+f"(d[85]), "+f"(d[86]), "+f"(d[87]),
        "+f"(d[88]), "+f"(d[89]), "+f"(d[90]), "+f"(d[91]), "+f"(d[92]), "+f"(d[93]), "+f"(d[94]), "+f"(d[95])
      : "r"(da), "n"(HA), "r"(db), "n"(HB), "r"(sc));
  }
};

struct FftConst {
  uint32_t f[2][4], fi[4][4];
  uint32_t ta[2][2], tb[2][2];
};
__device__ __forceinline__ void cis(int m, float scale, float& c, float& s) {
  const float a = (float)m * (-6.283185307179586f * scale);
  c = __cosf(a);
  s = __sinf(a);
}
__device__ __forceinline__ void fft_tables(uint32_t (&v)[12], int tw) {
  const int row = tw >> 2, ch = tw & 3;
#pragma unroll
  for (int i = 0; i < 4; i++) {
    float c[2], s[2], x[2];
#pragma unroll
    for (int e = 0; e < 2; e++) {
      cis((((32 * (8 * ch + 2 * i + e) + 15) * (4 * row - 63) + 2048) & 4095) - 2048, 1.f / 4096, c[e], s[e]);
      float gc, gs;
      cis((((row & 15) * (8 * (ch & 1) + 2 * i + e) + 8) & 15) - 8, 1.f / 16, gc, gs);
      x[e] = (row >> 4) == (ch >> 1) ? gc : (ch >> 1) ? gs : -gs;
    }
    v[i] = pack2(c[0] * 0.125f, c[1] * 0.125f);
    v[4 + i] = pack2(s[0] * 0.125f, s[1] * 0.125f);
    v[8 + i] = pack2(x[0], x[1]);
  }
#pragma unroll
  for (int i = 0; i < 12; i++) asm volatile("" : "+r"(v[i]));
}
__device__ __forceinline__ void fft_tables_store(const uint32_t (&v)[12], uint32_t sb, int tw) {
  const int row = tw >> 2;
  const uint32_t x = ((tw ^ (row >> 1)) & 3) << 4, a = sb + OFF_FT + (16 * (row >> 3) + (row & 7)) * 64 + x;
  sts128(a, v[0], v[1], v[2], v[3]);
  sts128(a + 512, v[4], v[5], v[6], v[7]);
  sts128(sb + OFF_GT + row * 64 + x, v[8], v[9], v[10], v[11]);
}
__device__ __forceinline__ void fft_twiddles(uint32_t (&v)[2], int tw) {
  float a[2], s[2];
#pragma unroll
  for (int i = 0; i < 2; i++) {
    float c;
    cis((2 * (2 * (tw & 3) + i) - 15) * (4 * (tw >> 2) - 63), 1.f / 4096, c, s[i]);
    a[i] = __fdividef(-s[i], 1.f + c);
  }
  v[0] = pack2(a[0], a[1]);
  v[1] = pack2(s[0], s[1]);
  asm volatile("" : "+r"(v[0]), "+r"(v[1]));
}
__device__ __forceinline__ void fft_matrices(FftConst& k, uint32_t sb, int w, int lane) {
  const uint32_t x = (lane >> 1) & 3;
  const uint2 t0 = lds64(sb + OFF_TT + 256 * w + 8 * lane), t1 = lds64(sb + OFF_TT + 256 * w + 8 * (lane ^ 3));
  k.ta[0][0] = t0.x;
  k.tb[0][0] = t0.y;
  k.ta[1][1] = __byte_perm(t1.x, 0, 0x1032);
  k.tb[1][1] = __byte_perm(t1.y, 0, 0x1032);
#pragma unroll
  for (int j = 0; j < 2; j++) {
    k.ta[1 - j][j] = k.ta[j][j] ^ 0x80008000u;
    k.tb[1 - j][j] = k.tb[j][j] ^ 0x80008000u;
    asm volatile("" : "+r"(k.ta[0][j]), "+r"(k.tb[0][j]), "+r"(k.ta[1][j]), "+r"(k.tb[1][j]));
  }
#pragma unroll
  for (int i = 0; i < 2; i++) {
    ldsm4(k.f[i], sb + OFF_FT + (16 * w + (lane & 15)) * 64 + (((2 * i + (lane >> 4)) ^ x) << 4));
    ldsm4t(k.fi[i], sb + OFF_FT + (32 * i + lane) * 64 + ((w ^ x) << 4));
#pragma unroll
    for (int j = 0; j < 4; j++) {
      k.fi[2 + i][j] = (j & 1) ? k.fi[i][j - 1] ^ 0x80008000u : k.fi[i][j + 1];
      asm volatile("" : "+r"(k.fi[2 + i][j]));
    }
  }
}
__device__ __forceinline__ void rot(uint32_t& x, uint32_t& y, uint32_t a, uint32_t b) {
  x = bfma(a, y, x);
  y = bfma(b, x, y);
  x = bfma(a, y, x);
}
__device__ __forceinline__ void twiddle_fwd(uint32_t (&a)[4][4], float* d, const FftConst& k) {
#pragma unroll
  for (int q = 0; q < 4; q++)
#pragma unroll
    for (int j = 0; j < 2; j++) {
      const float* x = d + 8 * q + 4 * j;
      uint32_t re = pack2(x[0], x[1]), im = pack2(x[2], x[3]);
      rot(re, im, k.ta[0][j], k.tb[0][j]);
      a[q & 2][2 * j + (q & 1)] = re;
      a[(q & 2) + 1][2 * j + (q & 1)] = im;
    }
}
__device__ __forceinline__ void g_step(float* d, const uint32_t (&a)[4][4], uint32_t dre, uint32_t dim) {
  WgRS<32>::set<HI_SW64>(d, a[0], dre);
  WgRS<32>::set<HI_SW64>(d + 16, a[2], dre);
  WgRS<32>::mma<HI_SW64>(d, a[1], dim);
  WgRS<32>::mma<HI_SW64>(d + 16, a[3], dim);
  wg_commit();
}

__device__ __forceinline__ void products(uint32_t (&a)[4][4], const float* H, const float* U, int p) {
#pragma unroll
  for (int j = 0; j < 2; j++)
#pragma unroll
    for (int m = 2 * p; m < 2 * p + 2; m++) {
      float pr[2], pi[2];
#pragma unroll
      for (int x = 0; x < 2; x++)
#pragma unroll
        for (int q = 0; q <= m; q++) {
          const int ih = 16 * (q >> 1) + 2 * (q & 1) + 4 * j + x, iu = 16 * ((m - q) >> 1) + 2 * ((m - q) & 1) + 4 * j + x;
          pr[x] = q ? fmaf(H[ih], U[iu], pr[x]) : H[ih] * U[iu];
          pi[x] = q ? fmaf(H[ih], U[iu + 8], pi[x]) : H[ih] * U[iu + 8];
          pr[x] = fmaf(-H[ih + 8], U[iu + 8], pr[x]);
          pi[x] = fmaf(H[ih + 8], U[iu], pi[x]);
        }
      a[m & 2][2 * j + (m & 1)] = pack2(pr[0], pr[1]);
      a[(m & 2) + 1][2 * j + (m & 1)] = pack2(pi[0], pi[1]);
    }
}

__device__ __forceinline__ void conv_channel(const FftConst& k, uint32_t sb, int c, int wg, int w, int lane) {
  const uint32_t cb = sb + off_ch(c), bars = sb + OFF_BAR;
  const uint32_t du = desc_lo(cb, 1024), dg = desc_lo(sb + OFF_GT, 16), dz = desc_lo(cb + U_BYTES, 16);
  float U[32], H[32];
  uint32_t a[4][4], e[4][4];
  const float dv = __uint_as_float(lds32(sb + OFF_D + 4 * c));
  wg_fence();
  WgRS<64>::set<HI_SW32>(H, k.f[0], du + 256);
  WgRS<64>::mma<HI_SW32>(H, k.f[1], du + 256 + 32);
  wg_commit();
  wg_wait<0>();
  pin<32>(H);
  twiddle_fwd(a, H, k);
  if (ATT_GATE) mbar_wait(bars + 8 * (ATT_GATE == 1 ? B_ATTN : B_ATT2), 0);
  mbar_wait(bars + 8 * (B_U + (c < 3 ? c : 3)), 0);
  TSM(w == 0 && c < 3, 7 + wg);
  wg_fence();
  WgRS<64>::set<HI_SW32>(U, k.f[0], du);
  WgRS<64>::mma<HI_SW32>(U, k.f[1], du + 32);
  wg_commit();
  g_step(H, a, dg, dg + 64);
  wg_wait<1>();
  pin<32>(U);
  twiddle_fwd(e, U, k);
  wg_fence();
  g_step(U, e, dg, dg + 64);
  wg_wait<0>();
  pin<32>(U);
  pin<32>(H);
#pragma unroll
  for (int j = 0; j < 4; j++) H[4 * (j >> 1) + (j & 1)] += dv;
  float V[32];
#pragma unroll
  for (int p = 0; p < 2; p++) {
    products(a, H, U, p);
    wg_fence();
    WgRS<32>::set<HI_SW64>(V + 16 * p, a[2 * p], dg + 64);
    WgRS<32>::mma<HI_SW64>(V + 16 * p, a[2 * p + 1], dg);
    wg_commit();
  }
  const uint32_t za = cb + U_BYTES + (8 * w + (lane & 7)) * 128 + (((lane >> 3) ^ (lane & 7)) << 4);
  const uint32_t ya = cb + (lane >> 4) * 1024 + (8 * w + (lane & 7)) * 32 + ((((lane >> 3) ^ (lane >> 2)) & 1) << 4);
  wg_sync(1 + wg);
#pragma unroll
  for (int p = 0; p < 2; p++) {
    if (p == 0) wg_wait<1>();
    else wg_wait<0>();
    pin<16>(V + 16 * p);
#pragma unroll
    for (int i = 0; i < 4; i++) {
      const int j = i & 1;
      const float* x = V + 16 * p + 4 * j + (i & 2);
      e[p][i] = pack2(x[8], x[9]);
      e[2 + p][i] = pack2(x[0], x[1]);
      rot(e[p][i], e[2 + p][i], k.ta[1][j], k.tb[1][j]);
    }
    stsm4(za ^ (64 * p), e[p]);
    stsm4((za ^ (64 * p)) + 4096, e[2 + p]);
  }
  fence_async_smem();
  wg_sync(1 + wg);
  wg_fence();
  WgRS<64>::set<HI_SW128>(H, k.fi[0], dz);
#pragma unroll
  for (int ks = 1; ks < 4; ks++) WgRS<64>::mma<HI_SW128>(H, k.fi[ks], dz + 128 * ks);
  wg_commit();
  if (WO_GATE == 3 && lane == 0) mbar_arrive(bars + 8 * B_CVD);
  wg_wait<0>();
  pin<32>(H);
  if (WO_GATE == 4 && lane == 0) mbar_arrive(bars + 8 * B_CVD);
  TSIF(w == 0, 88 + c);
#pragma unroll
  for (int j = 0; j < 8; j++)
    a[j >> 2][j & 3] = j < 2 ? pack2(H[4 * j], H[4 * j + 1]) : pack2(H[4 * j] + H[4 * j - 6], H[4 * j + 1] + H[4 * j - 5]);
  stsm4(ya, a[0]);
  stsm4(ya + 2048, a[1]);
  fence_async_smem();
  __syncwarp();
}

__device__ __forceinline__ void prep_slab(uint4* res, const uint2* sw, uint32_t sb, int slab, int w, int lane) {
  const int t = lane & 3, tp = (lane & 7) >> 1, pos = 8 * tp + 2 * (((lane >> 3) + tp) & 3) + (lane & 1);
  const uint32_t base = sb + OFF_KVS + slab * KVS_BYTES + pos * 128;
  uint32_t kk[2][4][4], vv[2][4];
  mbar_wait(sb + OFF_BAR + 8 * (B_KV + slab), 0);
#pragma unroll
  for (int h = 0; h < 2; h++) {
#pragma unroll
    for (int j = 0; j < 4; j++) {
      const uint32_t a = base + 128 * j;
      ldsm4t(kk[h][j], a + (((w + 4 * h) ^ ((a >> 7) & 7)) << 4));
    }
    const uint32_t a = base + KVS_V;
    ldsm4t(vv[h], a + (((w + 4 * h) ^ ((a >> 7) & 7)) << 4));
  }
#pragma unroll
  for (int h = 0; h < 2; h++) {
    uint32_t (&k)[4][4] = kk[h];
    uint32_t (&v)[4] = vv[h];
    const uint32_t w0 = __byte_perm(sw[h].x, 0, 0x1010), w1 = __byte_perm(sw[h].x, 0, 0x3232);
    const uint32_t w2 = __byte_perm(sw[h].y, 0, 0x1010), w3 = __byte_perm(sw[h].y, 0, 0x3232);
#pragma unroll
    for (int m = 0; m < 4; m++)
      v[m] = bmul(badd(badd(badd(bmul(k[0][m], w3), bmul(k[1][m], w2)), bmul(k[2][m], w1)), bmul(k[3][m], w0)), v[m]);
    uint32_t a[4];
#pragma unroll
    for (int m = 0; m < 4; m++) a[m] = (t & 1) ? v[(m + 3) & 3] : v[m];
    res[h] = (t & 2) ? make_uint4(a[2], a[3], a[0], a[1]) : make_uint4(a[0], a[1], a[2], a[3]);
  }
}

__device__ __forceinline__ void prep_gate(const Params& p, uint32_t sb, int b, int w, int lane) {
  uint2 gw[5], x[4][5];
#pragma unroll
  for (int j = 0; j < 5; j++) gw[j] = ldg64(reinterpret_cast<const uint2*>(p.gate_w) + lane + 32 * j);
#pragma unroll
  for (int i = 0; i < 4; i++)
#pragma unroll
    for (int j = 0; j < 5; j++)
      x[i][j] = ldg64(reinterpret_cast<const uint2*>(p.q) + (16 * b + 4 * w + i) * (DIM / 4) + lane + 32 * j);
  float s[4];
#pragma unroll
  for (int i = 0; i < 4; i++) {
    s[i] = 0.f;
#pragma unroll
    for (int j = 0; j < 5; j++) {
      const uint32_t m0 = bmul(x[i][j].x, gw[j].x), m1 = bmul(x[i][j].y, gw[j].y);
      s[i] += (bf_lo(m0) + bf_hi(m0)) + (bf_lo(m1) + bf_hi(m1));
    }
  }
  const bool h = lane & 16, q = lane & 8;
  const float a = (h ? s[2] : s[0]) + __shfl_xor_sync(0xffffffffu, h ? s[0] : s[2], 16);
  const float c = (h ? s[3] : s[1]) + __shfl_xor_sync(0xffffffffu, h ? s[1] : s[3], 16);
  float z = (q ? c : a) + __shfl_xor_sync(0xffffffffu, q ? a : c, 8);
#pragma unroll
  for (int o = 4; o > 0; o >>= 1) z += __shfl_xor_sync(0xffffffffu, z, o);
  z = bf_lo(pack2(z, 0.f));
  z = bf_lo(pack2(__fdividef(1.f, 1.f + __expf(-z)), 0.f));
  if (G_TMA) {
    mbar_wait(sb + OFF_BAR + 8 * B_S3, 0);
    if ((lane & 7) == 0) asm volatile("st.shared.f32 [%0], %1;" ::"r"(sb + OFF_GATE + 64 * (b & 7) + 16 * w + (lane >> 1)), "f"(z) : "memory");
    fence_async_smem();
  } else if ((lane & 7) == 0) {
    g_gate[16 * b + 4 * w + (lane >> 3)] = z;
  }
}

__device__ __forceinline__ uint32_t bmax(uint32_t a, uint32_t b) {
  uint32_t d;
  asm("max.bf16x2 %0, %1, %2;" : "=r"(d) : "r"(a), "r"(b));
  return d;
}
__device__ __forceinline__ void softmax_two(const float (&l)[2][2], uint32_t& p0, uint32_t& p1) {
  constexpr float kScale = 0.22360679774997896f, kLog2e = 1.4426950408889634f;
  const uint32_t r0 = pack2(l[0][0], l[1][0]), r1 = pack2(l[0][1], l[1][1]);
  const uint32_t x0 = pack2(bf_lo(r0) * kScale, bf_hi(r0) * kScale), x1 = pack2(bf_lo(r1) * kScale, bf_hi(r1) * kScale);
  uint32_t m = bmax(x0, x1);
  m = bmax(m, __shfl_xor_sync(0xffffffffu, m, 1));
  m = bmax(m, __shfl_xor_sync(0xffffffffu, m, 2));
  const float m0 = bf_lo(m) * kLog2e, m1 = bf_hi(m) * kLog2e;
  p0 = pack2(ex2(bf_lo(x0) * kLog2e - m0), ex2(bf_lo(x1) * kLog2e - m0));
  p1 = pack2(ex2(bf_hi(x0) * kLog2e - m1), ex2(bf_hi(x1) * kLog2e - m1));
}

__device__ __forceinline__ void halo_read(uint32_t (&kpv)[10], uint32_t (&vpv)[10], uint32_t (&tg)[7], const uint4* hp) {
#pragma unroll
  for (int j = 0; j < 7; j++) {
    uint32_t x0, x1, x2;
    asm volatile("ld.relaxed.gpu.global.v4.u32 {%0, %1, %2, %3}, [%4];"
                 : "=r"(x0), "=r"(x1), "=r"(x2), "=r"(tg[j]) : "l"(hp + 32 * j) : "memory");
    if (j < 4) kpv[3 * j] = x0; else vpv[3 * j - 10] = x0;
    if (j < 3) kpv[3 * j + 1] = x1; else vpv[3 * j - 9] = x1;
    if (j < 3) kpv[3 * j + 2] = x2; else if (j < 6) vpv[3 * j - 8] = x2;
  }
}

template <int ROT>
__device__ __forceinline__ void pack_qkv(const float* acc, uint32_t (&qlo)[10], uint32_t (&qhi)[10], uint32_t (&klo)[10],
                                         uint32_t (&khi)[10], uint32_t (&vlo)[10], uint32_t (&vhi)[10]) {
#pragma unroll
  for (int j = 0; j < 10; j++) {
    const int x = (j + ROT) % 10, tq = x < 8 ? x : 16 + x, tk = x < 8 ? 8 + x : 18 + x, tv = x < 8 ? 16 + x : 20 + x;
    khi[j] = pack2(acc[4 * tk + 2], acc[4 * tk + 3]);
    vhi[j] = movm(pack2(acc[4 * tv + 2], acc[4 * tv + 3]));
    qlo[j] = pack2(acc[4 * tq], acc[4 * tq + 1]);
    qhi[j] = pack2(acc[4 * tq + 2], acc[4 * tq + 3]);
    klo[j] = pack2(acc[4 * tk], acc[4 * tk + 1]);
    vlo[j] = pack2(acc[4 * tv], acc[4 * tv + 1]);
    asm volatile("" : "+r"(khi[j]), "+r"(qlo[j]), "+r"(qhi[j]), "+r"(klo[j]), "+r"(vlo[j]));
  }
}

template <int ROT> __device__ __forceinline__ void halo_send(const float* acc, uint4* ho, uint32_t tag) {
#pragma unroll
  for (int j = 0; j < 7; j++) {
    uint32_t x[3];
#pragma unroll
    for (int e = 0; e < 3; e++) {
      const int i = 3 * j + e, y = (i % 10 + ROT) % 10, tk = y < 8 ? 8 + y : 18 + y, tv = y < 8 ? 16 + y : 20 + y;
      x[e] = i < 10 ? pack2(acc[4 * tk + 2], acc[4 * tk + 3]) : i < 20 ? movm(pack2(acc[4 * tv + 2], acc[4 * tv + 3])) : 0u;
    }
    asm volatile("st.relaxed.gpu.global.v4.u32 [%0], {%1, %2, %3, %4};" ::"l"(ho + 32 * j), "r"(x[0]), "r"(x[1]), "r"(x[2]), "r"(tag) : "memory");
  }
}

__device__ __forceinline__ void attention(float* acc, uint32_t sb, int b, int par, int w, int lane, uint32_t tag, uint32_t zero) {
  const int g = lane >> 2, t = lane & 3;
  uint32_t klo[10], khi[10], vlo[10], vhi[10], qlo[10], qhi[10], kpv[10], vpv[10];
  if (HALO_FIRST && w == 3 && b < NCTA - 8) {
    uint4* ho = g_halo + (b * 2 + par) * 224 + lane;
    if (tail_first(b & 7)) halo_send<8>(acc, ho, tag);
    else halo_send<0>(acc, ho, tag);
    TSIF(par == 0, 76);
    pin<120>(acc);
  }
  if (tail_first(b & 7)) pack_qkv<8>(acc, qlo, qhi, klo, khi, vlo, vhi);
  else pack_qkv<0>(acc, qlo, qhi, klo, khi, vlo, vhi);
  const uint32_t xa = sb + OFF_KVX + (par * 3) * 2560 + lane * 16;
  if (w < 3) {
    sts128(xa + w * 2560, khi[0], khi[1], khi[2], khi[3]);
    sts128(xa + w * 2560 + 512, khi[4], khi[5], khi[6], khi[7]);
    sts128(xa + w * 2560 + 1024, khi[8], khi[9], vhi[0], vhi[1]);
    sts128(xa + w * 2560 + 1536, vhi[2], vhi[3], vhi[4], vhi[5]);
    sts128(xa + w * 2560 + 2048, vhi[6], vhi[7], vhi[8], vhi[9]);
  } else if (!HALO_FIRST && b < NCTA - 8) {
    uint4* ho = g_halo + (b * 2 + par) * 224 + lane;
#pragma unroll
    for (int j = 0; j < 7; j++) {
      const uint32_t x0 = j < 4 ? khi[3 * j] : vhi[3 * j - 10], x1 = j < 3 ? khi[3 * j + 1] : vhi[3 * j - 9];
      const uint32_t x2 = j < 3 ? khi[3 * j + 2] : j < 6 ? vhi[3 * j - 8] : 0u;
      asm volatile("st.relaxed.gpu.global.v4.u32 [%0], {%1, %2, %3, %4};" ::"l"(ho + 32 * j), "r"(x0), "r"(x1), "r"(x2), "r"(tag) : "memory");
    }
  }
  TSIF(par == 0 && w == 1, 64);
  TSIF(par == 0 && w == 3 && !HALO_FIRST, 76);
#pragma unroll
  for (int j = 0; j < 10; j++) vlo[j] = movm(vlo[j]);
  const bool far0 = 2 * t > g, far1 = 2 * t + 1 > g;
  const uint32_t mfar = (far0 ? 0x0000FFFFu : 0u) | (far1 ? 0xFFFF0000u : 0u);
  float slo[4][2], shi[4][2], lg[2][2];
  uint32_t phi[4], plo[4], qml[4], qmh[4];
#pragma unroll
  for (int h = 0; h < 4; h++) {
    const int f = h == 0 ? 0 : h == 1 ? 3 : h == 2 ? 5 : 8, hf = h < 2 ? 2 : 7;
    const bool mine = (h & 1) ? t >= 2 : t < 2;
    qml[h] = mine ? qlo[hf] : 0u;
    qmh[h] = mine ? qhi[hf] : 0u;
    float a[4] = {0.f, 0.f, 0.f, 0.f}, c[4] = {0.f, 0.f, 0.f, 0.f};
    mma16816(a, qlo[f], qhi[f], qlo[f + 1], qhi[f + 1], klo[f], klo[f + 1]);
    mma16816(c, qlo[f], qhi[f], qlo[f + 1], qhi[f + 1], khi[f], khi[f + 1]);
    mma1688(a, qml[h], qmh[h], klo[hf]);
    mma1688(c, qml[h], qmh[h], khi[hf]);
    slo[h][0] = a[0];
    slo[h][1] = a[1];
    shi[h][0] = lg[h & 1][0] = far0 ? a[2] : c[2];
    shi[h][1] = lg[h & 1][1] = far1 ? a[3] : c[3];
    if (!ATT_MERGE && (h & 1)) softmax_two(lg, phi[h - 1], phi[h]);
  }
  TSIF(par == 0 && w == 1, 65);
  if (ATT_GATE == 3 && lane == 0) mbar_arrive(sb + OFF_BAR + 8 * B_ATT2 + (phi[3] & zero));
  wg_sync(1 + par);
  TSIF(par == 0 && w == 1, 66);
  const bool nohist = (w == 0) && (b < 8);
  const uint4* hp = g_halo + ((b - 8) * 2 + par) * 224 + lane;
  uint32_t tg[7];
  if (w > 0) {
    const uint4 v0 = lds128(xa + (w - 1) * 2560), v1 = lds128(xa + (w - 1) * 2560 + 512), v2 = lds128(xa + (w - 1) * 2560 + 1024);
    const uint4 v3 = lds128(xa + (w - 1) * 2560 + 1536), v4 = lds128(xa + (w - 1) * 2560 + 2048);
    kpv[0] = v0.x; kpv[1] = v0.y; kpv[2] = v0.z; kpv[3] = v0.w; kpv[4] = v1.x; kpv[5] = v1.y; kpv[6] = v1.z; kpv[7] = v1.w;
    kpv[8] = v2.x; kpv[9] = v2.y; vpv[0] = v2.z; vpv[1] = v2.w; vpv[2] = v3.x; vpv[3] = v3.y; vpv[4] = v3.z; vpv[5] = v3.w;
    vpv[6] = v4.x; vpv[7] = v4.y; vpv[8] = v4.z; vpv[9] = v4.w;
  } else if (nohist) {
#pragma unroll
    for (int j = 0; j < 10; j++) kpv[j] = vpv[j] = 0u;
  } else {
    TSIF(par == 0, 77);
    halo_read(kpv, vpv, tg, hp);
  }
  if (w == 0 && !nohist) {
    int spins = 0;
    while (true) {
      bool ok = true;
#pragma unroll
      for (int j = 0; j < 7; j++) ok = ok && tg[j] == tag;
      if (__all_sync(0xffffffffu, ok) || ++spins > SPIN_LIMIT) break;
      halo_read(kpv, vpv, tg, hp);
    }
    TSIF(par == 0, 79);
  }
#pragma unroll
  for (int h = 0; h < 4; h++) {
    const int f = h == 0 ? 0 : h == 1 ? 3 : h == 2 ? 5 : 8, hf = h < 2 ? 2 : 7;
    float a[4] = {0.f, 0.f, 0.f, 0.f};
    mma16816(a, qlo[f], qhi[f], qlo[f + 1], qhi[f + 1], kpv[f], kpv[f + 1]);
    mma1688(a, qml[h], qmh[h], kpv[hf]);
    const float ninf = __int_as_float(0xff800000);
    lg[h & 1][0] = far0 ? (nohist ? ninf : a[0]) : slo[h][0];
    lg[h & 1][1] = far1 ? (nohist ? ninf : a[1]) : slo[h][1];
    if (h & 1) {
      softmax_two(lg, plo[h - 1], plo[h]);
      if (ATT_MERGE) {
        const float lh[2][2] = {{shi[h - 1][0], shi[h - 1][1]}, {shi[h][0], shi[h][1]}};
        softmax_two(lh, phi[h - 1], phi[h]);
      }
    }
  }
  TSIF(par == 0 && w <= 1, 67 + w);
  if (ATT_GATE == 2 && lane == 0) mbar_arrive(sb + OFF_BAR + 8 * B_ATT2 + (plo[3] & zero));
  uint32_t ov[20];
#pragma unroll
  for (int hp = 0; hp < 2; hp++) {
    const int hf = hp ? 7 : 2;
    float sh[4] = {0.f, 0.f, 0.f, 0.f}, i0 = 0.f, i1 = 0.f;
#pragma unroll
    for (int e = 0; e < 2; e++) {
      const int h = 2 * hp + e, f = h == 0 ? 0 : h == 1 ? 3 : h == 2 ? 5 : 8;
      const uint32_t a0 = plo[h] & mfar, a2 = plo[h] & ~mfar, a3 = phi[h] & mfar, c1 = phi[h] & ~mfar;
      float sum[4] = {0.f, 0.f, 0.f, 0.f};
      mma1688(sum, plo[h], phi[h], 0x3F803F80u);
      const float r0 = rcp(sum[0]), r1 = rcp(sum[2]);
#pragma unroll
      for (int j = f; j < f + 2; j++) {
        float o[4] = {0.f, 0.f, 0.f, 0.f};
        mma16816(o, a0, 0u, a2, a3, vpv[j], vlo[j]);
        mma1688(o, 0u, c1, vhi[j]);
        ov[2 * j] = pack2(o[0] * r0, o[1] * r0);
        ov[2 * j + 1] = pack2(o[2] * r1, o[3] * r1);
      }
      const bool mine = e ? g >= 4 : g < 4;
      mma16816(sh, a0, 0u, a2, a3, mine ? vpv[hf] : 0u, mine ? vlo[hf] : 0u);
      mma1688(sh, 0u, c1, mine ? vhi[hf] : 0u);
      if (e == 0 || t >= 2) {
        i0 = r0;
        i1 = r1;
      }
    }
    ov[2 * hf] = pack2(sh[0] * i0, sh[1] * i0);
    ov[2 * hf + 1] = pack2(sh[2] * i1, sh[3] * i1);
  }
  if (ATT_GATE == 4 && lane == 0) mbar_arrive(sb + OFF_BAR + 8 * B_ATT2 + (ov[19] & zero));
  TS(32 + 4 * par + w);
  mbar_wait(sb + OFF_BAR + 8 * B_P1, 0);
  const uint32_t oa = sb + OFF_OA + (lane >> 4) * 2048 + (32 * w + 2 * (lane & 15) + par) * 16;
#pragma unroll
  for (int j = 0; j < 5; j++) stsm4(oa + 4096 * j, ov + 4 * j);
  TSIF(par == 0 && w == 0, 120);
  fence_async_smem();
  TSIF(par == 0 && w == 0, 121);
  __syncwarp();
  if (lane == 0) mbar_arrive(sb + OFF_BAR + 8 * B_ATTN);
  TSM(w == 0 || w == 2, 122 + par + (w == 2 ? 3 : 0));
}

struct Maps {
  CUtensorMap x, wm, wt, k, v, y, wo, qm, qt, om, ot, u;
};

__device__ __forceinline__ void load_stage(uint32_t sb, int kb, int b, const Maps& m) {
  const uint32_t st = sb + (kb & 3) * STAGE_BYTES, bar = sb + OFF_BAR + 8 * (B_FULL1 + (kb & 3));
  const int r = b >> 3, hg = b & 7, slab = kb - KV_KB;
  const bool kv = slab >= 0 && slab < 5;
  const uint32_t kbar = sb + OFF_BAR + 8 * (B_KV + slab), dst = sb + OFF_KVS + slab * KVS_BYTES;
  mbar_expect_tx(bar, STAGE_BYTES);
  if (kv) mbar_expect_tx(kbar, KVS_BYTES);
  tma_3d(st, &m.x, 64 * kb, 64 * r, 0, bar);
  if (kv && KV_MIX) tma_3d(dst, &m.k, 0, 32 * (b >> 1) - 3, 2 * slab + (b & 1), kbar);
  tma_3d(st + ST_W, &m.wm, 80 * hg + (tail_first(hg) ? 16 : 0), 64 * kb, 0, bar);
  if (kv && KV_MIX) tma_3d(dst + KVS_V, &m.v, 0, 32 * (b >> 1), 2 * slab + (b & 1), kbar);
  tma_3d(st + ST_WT, &m.wt, 80 * hg + (tail_first(hg) ? 0 : 64), 64 * kb, 0, bar);
  if (kv && !KV_MIX) tma_3d(dst, &m.k, 0, 32 * (b >> 1) - 3, 2 * slab + (b & 1), kbar);
  if (kv && !KV_MIX) tma_3d(dst + KVS_V, &m.v, 0, 32 * (b >> 1), 2 * slab + (b & 1), kbar);
}

__global__ void __launch_bounds__(NTHR, 1) fused_kernel(const __grid_constant__ Maps m, const Params p) {
  extern __shared__ __align__(1024) uint8_t smem[];
  const uint32_t sb = (uint32_t)__cvta_generic_to_shared(smem);
  const uint32_t bars = sb + OFF_BAR;
  const int tid = threadIdx.x, lane = tid & 31;
  int b = blockIdx.x;
  if (BMAP == 1) b = (((b & 63) >> 3) * 2 + (b & 1)) * 8 + (((b < 64 ? 0x6521 : 0x7430) >> (4 * ((b >> 1) & 3))) & 7);
  if (BMAP == 2) b = ((b & 63) >> 2) * 8 + (((b < 64 ? 0x6521 : 0x7430) >> (4 * (b & 3))) & 7);
  if (BMAP == 3) b = (((b & 63) >> 3) * 2 + (b & 1)) * 8 + (((b < 64 ? 0x7430 : 0x6521) >> (4 * ((b >> 1) & 3))) & 7);
  if (BMAP == 4) b = (((b >> 4) * 2 + (b & 1)) * 8) + ((b >> 1) & 7);
  if (BMAP == 5) b = 127 - b;
  const int r = b >> 3, hg = b & 7;

  if (tid == T_ISSUE) {
    TSM(true, 0);
#pragma unroll
    for (int i = 0; i < 4; i++) mbar_init(bars + 8 * (B_FULL1 + i), 1);
#pragma unroll
    for (int i = 0; i < 3; i++) mbar_init(bars + 8 * (B_KV + i), 1);
    fence_async_smem();
#pragma unroll 1
    for (int kb = 0; kb <= PRE2; kb++) load_stage(sb, kb, b, m);
  } else if (tid >= T_PF && tid < T_PF + 12) {
    tm_prefetch(&m.x + (tid - T_PF));
  } else if (tid == T_INIT) {
#pragma unroll
    for (int i = 0; i < 4; i++) mbar_init(bars + 8 * (B_EMPTY1 + i), 8);
#pragma unroll
    for (int i = 0; i < 8; i++) mbar_init(bars + 8 * (B_FULL2 + i), 1);
#pragma unroll
    for (int i = 0; i < 4; i++) mbar_init(bars + 8 * (B_EMPTY2 + i), 8);
#pragma unroll
    for (int i = 0; i < 4; i++) mbar_init(bars + 8 * (B_U + i), 1);
    mbar_init(bars + 8 * B_HA, 4);
    mbar_init(bars + 8 * B_GATE, 4);
    mbar_init(bars + 8 * B_HB, 1);
    mbar_init(bars + 8 * B_KVD, 4);
    mbar_init(bars + 8 * B_QF, 1);
    mbar_init(bars + 8 * B_ATTN, 8);
    mbar_init(bars + 8 * B_ATT2, 8);
    mbar_init(bars + 8 * B_P1, 8);
    mbar_init(bars + 8 * B_C34, 1);
    mbar_init(bars + 8 * B_YRB, 1);
#pragma unroll
    for (int i = 0; i < 5; i++) mbar_init(bars + 8 * (B_YST + i), 4);
#pragma unroll
    for (int i = 0; i < 5; i++) mbar_init(bars + 8 * (B_US + i), U_TMA ? 4 : i == 2 ? 20 : 1);
    mbar_init(bars + 8 * B_YSIG, 1);
    mbar_init(bars + 8 * B_YFULL, 1);
    mbar_init(bars + 8 * B_EPOCH, 1);
    mbar_init(bars + 8 * B_PREP, 4);
    mbar_init(bars + 8 * B_USIG, 1);
    mbar_init(bars + 8 * B_WST, 1);
#pragma unroll
    for (int i = 3; i < 5; i++) mbar_init(bars + 8 * (B_KV + i), 1);
    mbar_init(bars + 8 * B_E3, 8);
    mbar_init(bars + 8 * B_LAST, 1);
    mbar_init(bars + 8 * B_OSIG, 1);
    mbar_init(bars + 8 * B_WOP, 1);
    fence_async_smem();
  }
  const int warp = __shfl_sync(0xffffffffu, tid >> 5, 0), wg = warp >> 2, w = warp & 3;
  __syncthreads();

  if (wg == 3) {
    asm volatile("setmaxnreg.dec.sync.aligned.u32 56;");
    if (w == 0) {
      if (lane == 0) {
#pragma unroll 1
        for (int kb = 1 + PRE2; kb < 10; kb++) {
          if (kb >= 4) mbar_wait(bars + 8 * (kb == 7 ? B_E3 : B_EMPTY1 + (kb & 3)), (kb >> 3) & 1);
          TSIF(kb >= 4, 44 + kb);
          load_stage(sb, kb, b, m);
          TSIF(kb == 3, 60);
          if (kb == TRIG_KB) mbar_arrive(bars + 8 * B_LAST);
        }
        mbar_wait(bars + 8 * B_WOP, 0);
        mbar_wait(bars + 8 * WL_TRIG, 0);
        mbar_wait(bars + 8 * B_EPOCH, 0);
        flag_wait(g_cnt + C_W + 32 * hg, (lds32(sb + OFF_EPOCH) + 1) * 16);
        TS(30);
#pragma unroll 1
        for (int j = 0; j < 8; j++) {
          if (j >= 6) mbar_wait(bars + 8 * (B_EMPTY2 + j - 6), 0);
          if (j == 4) mbar_wait(bars + 8 * B_ATTN, 0);
          TSIF(j >= 6, 100 + j);
          if (RF_GATE && j == 6) mbar_wait(bars + 8 * B_YSIG, 0);
          mbar_expect_tx(bars + 8 * (B_FULL2 + j), j == 0 ? WO_BYTES : j == 5 ? O_BYTES + WO_BYTES + 512 : O_BYTES + WO_BYTES);
          bulk_load(sb + off_w(j), g_WO + (hg * 8 + step_src(hg, j)) * 800, WO_BYTES, bars + 8 * (B_FULL2 + j));
        }
        mbar_wait(bars + 8 * (B_EMPTY2 + Q_SLOT), 0);
        mbar_expect_tx(bars + 8 * B_QF, O_BYTES);
        tma_2d(sb + OFF_QS, &m.qm, 80 * hg, 128 * r, bars + 8 * B_QF);
        if (!QBOX) tma_2d(sb + OFF_QT, &m.qt, 80 * hg + 64, 128 * r, bars + 8 * B_QF);
      }
    } else if (w == 1) {
      unsigned epoch = 0;
      if (lane == 0) {
        epoch = atomicAdd(g_cnt + C_LAUNCH, 1u) / NCTA;
        asm volatile("st.shared.u32 [%0], %1;" ::"r"(sb + OFF_EPOCH), "r"(epoch) : "memory");
        mbar_arrive(bars + 8 * B_EPOCH);
        mbar_wait(bars + 8 * B_KVD, 0);
        mbar_expect_tx(bars + 8 * B_HB, 5 * 4096);
#pragma unroll 1
        for (int c = 0; c < 5; c++) {
          if (c == 3) mbar_wait(bars + 8 * B_S3, 0);
          bulk_load(sb + off_ch(c) + U_BYTES, p.ssm_k + (5 * b + c) * SEQ, 4096, bars + 8 * B_HB);
        }
#pragma unroll
        for (int c = 0; c < 4; c++) mbar_expect_tx(bars + 8 * (B_U + c), c < 3 ? U_BYTES : 2 * U_BYTES);
        const uint4* usrc = g_U + 5 * b * U_PITCH;
        mbar_wait(bars + 8 * B_USIG, 0);
        flag_wait(g_cnt + C_PREP + 32 * (b & 15), (epoch + 1) * NCTA);
        TS(23);
#pragma unroll
        for (int c = 0; c < 5; c++) {
          if (c == 3 && U_TRIM) mbar_wait(bars + 8 * (B_U + 2), 0);
          bulk_load(sb + off_ch(c), usrc + c * U_PITCH, U_BYTES, bars + 8 * (B_U + (c < 3 ? c : 3)));
          TSIF(c == 0 || c == 4, 116 + (c >> 2));
        }
      }
      epoch = __shfl_sync(0xffffffffu, epoch, 0);
      if (lane < 8) {
        const int src = (b & ~7) | step_src(hg, lane);
        mbar_wait(bars + 8 * OP_TRIG, 0);
        TS(20);
        bool seen = false;
#pragma unroll 1
        for (int spins = 0; spins < SPIN_LIMIT; spins++) {
          const bool now = !seen && (int)(flag_read(g_cnt + C_O + 32 * src) - (epoch + 1)) >= 0;
          if (now && lane >= 1 && lane < 4) bulk_load(sb + off_o(lane), g_O + src * 1280, O_BYTES, bars + 8 * (B_FULL2 + lane));
          seen = seen || now;
          if (__all_sync(0xff, seen)) break;
        }
        TS(21);
        if (lane == 5) bulk_load(sb + OFF_GATE, g_gate + 128 * r, 512, bars + 8 * (B_FULL2 + 5));
#pragma unroll 1
        for (int j = 4; j < 8; j++) {
          if (lane == j) {
            mbar_wait(bars + 8 * (j < 6 ? B_C34 : B_EMPTY2 + j - 6), 0);
            if (RF_GATE && j == 6) mbar_wait(bars + 8 * B_YSIG, 0);
            bulk_load(sb + off_o(j), g_O + src * 1280, O_BYTES, bars + 8 * (B_FULL2 + j));
          }
          __syncwarp(0xff);
        }
        TS(22);
      }
    } else if (w == 2) {
      mbar_wait(bars + 8 * B_PREP, 0);
      flag_signal(g_cnt + C_PREP, 16, lane);
      TS(25);
      if (lane == 0) mbar_arrive(bars + 8 * B_USIG);
      mbar_wait(bars + 8 * B_GATE, 0);
      if (G_TMA) {
        if (lane == 0) {
          asm volatile("cp.async.bulk.global.shared::cta.bulk_group [%0], [%1], 64;\ncp.async.bulk.commit_group;\n"
                       "cp.async.bulk.wait_group.read 0;" ::"l"(g_gate + 16 * b), "r"(sb + OFF_GATE + 64 * hg) : "memory");
          bulk_load(sb + OFF_GATE + 64 * hg, g_gate + 16 * b, 64, bars + 8 * B_ORB);
        }
      } else if (((NOMB & 1) || O_RB) && lane == 0) {
        asm volatile("fence.release.gpu;" ::: "memory");
      }
      mbar_wait(bars + 8 * B_ATTN, 0);
      if (lane == 0) {
        if (O_DEFER) mbar_wait(bars + 8 * (B_U + 3), 0);
        asm volatile("cp.async.bulk.global.shared::cta.bulk_group [%0], [%1], 20480;\ncp.async.bulk.commit_group;"
                     ::"l"(g_O + b * 1280), "r"(sb + OFF_OA) : "memory");
        if (O_RB == 2) {
          asm volatile("cp.async.bulk.wait_group.read 0;" ::: "memory");
          mbar_expect_tx(bars + 8 * B_ORB, O_BYTES + 64 * G_TMA);
          bulk_load(sb + OFF_OA, g_O + b * 1280, O_BYTES, bars + 8 * B_ORB);
          mbar_wait(bars + 8 * B_ORB, 0);
          flag_bump(g_cnt + C_O + 32 * b);
        } else if (O_RB) asm volatile("cp.async.bulk.wait_group.read 0;" ::: "memory");
        else asm volatile("cp.async.bulk.wait_group 0;\nfence.proxy.async.global;" ::: "memory");
      }
      TS(74);
      if (O_RB == 2) {
      } else if (O_RB) {
        __syncwarp();
        unsigned v[5];
#pragma unroll
        for (int c = 0; c < 5; c++) v[c] = flag_read(reinterpret_cast<const unsigned*>(g_O + b * 1280 + 256 * c + 8 * lane + 7));
        const unsigned dep = __reduce_or_sync(0xffffffffu, (v[0] ^ v[1] ^ v[2] ^ v[3] ^ v[4]) & p.zero);
        if (lane == 0) flag_bump(g_cnt + C_O + 32 * b + dep);
      } else if (!(NOMB & 1)) flag_signal(g_cnt + C_O + 32 * b, 1, lane);
      else if (lane == 0) flag_bump(g_cnt + C_O + 32 * b);
      TS(26);
      if (lane == 0) mbar_arrive(bars + 8 * B_OSIG);

    } else {
      if (lane == 0) {
        uint4* dst = g_WO + (hg * 8 + (r >> 1)) * 800 + (r & 1) * 80;
        if (WPF) {
          mbar_wait(bars + 8 * WPF, 0);
          if (WPF_LIN)
            asm volatile("cp.async.bulk.prefetch.L2.global [%0], 6400;" ::"l"(p.wo + b * 3200) : "memory");
          else
            asm volatile("cp.async.bulk.prefetch.tensor.3d.L2.global [%0, {%1, %2, %3}];" ::"l"(&m.wo), "r"(0), "r"(40 * r), "r"(5 * hg) : "memory");
        }
        mbar_wait(bars + 8 * B_P1, 0);
        mbar_wait(bars + 8 * WB_TRIG, 0);
        mbar_expect_tx(bars + 8 * B_WST, WO_BYTES / 2);
        tma_3d(sb + OFF_WS, &m.wo, 0, 40 * r, 5 * hg, bars + 8 * B_WST);
        mbar_wait(bars + 8 * B_WST, 0);
        mbar_wait(bars + 8 * WO_TRIG, 0);
#pragma unroll 1
        for (int n = 0; n < 5; n++)
          asm volatile("cp.async.bulk.global.shared::cta.bulk_group [%0], [%1], 1280;" ::"l"(dst + 160 * n), "r"(sb + OFF_WS + 1280 * n) : "memory");
        if (W_RB) {
          asm volatile("cp.async.bulk.commit_group;\ncp.async.bulk.wait_group.read 0;" ::: "memory");
          mbar_expect_tx(bars + 8 * B_WST, WO_BYTES / 2);
#pragma unroll 1
          for (int n = 0; n < 5; n++) bulk_load(sb + OFF_WS + 1280 * n, dst + 160 * n, 1280, bars + 8 * B_WST);
          mbar_wait(bars + 8 * B_WST, 1);
        } else {
          asm volatile("cp.async.bulk.commit_group;\ncp.async.bulk.wait_group 0;\nfence.proxy.async.global;" ::: "memory");
          if (!(NOMB & 4)) asm volatile("fence.release.gpu;" ::: "memory");
        }
        flag_bump(g_cnt + C_W + 32 * hg);
        mbar_arrive(bars + 8 * B_WOP);
        TS(71);
        mbar_expect_tx(bars + 8 * B_C34, 3 * U_BYTES);
        mbar_expect_tx(bars + 8 * B_YRB, 2 * U_BYTES);
#pragma unroll 1
        for (int c = 0; c < 5; c++) {
          mbar_wait(bars + 8 * (B_YST + c), 0);
          asm volatile("cp.async.bulk.global.shared::cta.bulk_group [%0], [%1], 4096;\ncp.async.bulk.commit_group;\n"
                       "cp.async.bulk.wait_group.read 0;" ::"l"(g_Y + (5 * b + c) * Y_PITCH), "r"(sb + off_ch(c)) : "memory");
          bulk_load(sb + off_ch(c), g_Y + (5 * b + c) * Y_PITCH, U_BYTES, bars + 8 * (c < 3 ? B_C34 : B_YRB));
        }
        TS(75);
        mbar_wait(bars + 8 * B_C34, 0);
        mbar_wait(bars + 8 * B_YRB, 0);
        flag_bump(g_cnt + C_Y + 32 * (b >> 4));
        TS(27);
        mbar_arrive(bars + 8 * B_YSIG);
        mbar_expect_tx(bars + 8 * B_YFULL, 20480);
        flag_wait(g_cnt + C_Y + 32 * hg, (lds32(sb + OFF_EPOCH) + 1) * 16);
        TS(24);
        tma_2d(sb + OFF_YT, &m.y, 128 * r, 80 * hg, bars + 8 * B_YFULL);
        tma_2d(sb + OFF_YT + 10240, &m.y, 128 * r + 64, 80 * hg, bars + 8 * B_YFULL);
      }
    }
  } else {
    asm volatile("setmaxnreg.inc.sync.aligned.u32 152;");
    if (wg < 2) {
      float acc[120];
#pragma unroll
      for (int i = 0; i < 120; i++) acc[i] = 0.f;
      const uint32_t da = desc_lo(sb + wg * 8192, 16), db = desc_lo(sb + ST_W, 8192), dc = desc_lo(sb + ST_WT, 2048);
      if (PW1) pin<120>(acc);
      if (PW1 == 2) mbar_wait(bars + 8 * B_FULL1, 0);
#pragma unroll 1
      for (int kb = 0; kb < 10; kb++) {
        mbar_wait(bars + 8 * (B_FULL1 + (kb & 3)), (kb >> 2) & 1);
        const uint32_t so = (kb & 3) * (STAGE_BYTES >> 4);
        wg_fence();
#pragma unroll
        for (int k = 0; k < 4; k++) {
          WgSST<192>::mma<HI_SW128, HI_SW128>(acc, da + so + 2 * k, db + so + 128 * k, 1);
          WgSST<48>::mma<HI_SW128, HI_SW32>(acc + 96, da + so + 2 * k, dc + so + 32 * k, 1);
        }
        wg_commit();
        wg_wait<1>();
        if (kb > 0 && lane == 0) mbar_arrive(bars + 8 * (kb == 4 ? B_E3 : B_EMPTY1 + ((kb - 1) & 3)));
      }
      mbar_wait(bars + 8 * B_EPOCH, 0);
      const uint32_t tag = lds32(sb + OFF_EPOCH) + 1;
      mbar_wait(bars + 8 * B_S3, 0);
      wg_wait<0>();
      pin<120>(acc);
      if (lane == 0) mbar_arrive(bars + 8 * B_P1);
      TSM(w == 0, 3 + wg);
      attention(acc, sb, b, wg, w, lane, tag, p.zero);
    } else {
      const int tw = tid & 127, chl = 64 * (b & 1) + 8 * w + (lane >> 2);
      uint4* up = g_U + chl * U_PITCH + ((4 * (b >> 1) + (lane & 3)) ^ ((b >> 2) & 1));
      uint2 sw[10];
      uint32_t dv = 0;
      if (lane < 5) dv = __ldg(reinterpret_cast<const unsigned short*>(p.ssm_D) + 5 * b + lane);
#pragma unroll
      for (int i = 0; i < 10; i++) sw[i] = ldg64(reinterpret_cast<const uint2*>(p.shift_k) + chl + 128 * (i >> 1) + 32 * (i & 1));
      uint32_t tab[12];
      uint32_t tt[2];
      fft_tables(tab, tw);
      fft_twiddles(tt, tw);
      uint4 res[10];
#pragma unroll
      for (int i = 0; i < 10; i++) res[i] = make_uint4(0, 0, 0, 0);
#pragma unroll 1
      for (int slab = 0; slab < 5; slab++) {
#pragma unroll
        for (int i = 0; i < 8; i++) res[i] = res[i + 2];
        prep_slab(res + 8, sw, sb, slab, w, lane);
        TSIF(w == 0, 99 + 4 * slab);
#pragma unroll
        for (int i = 0; i < 8; i++) sw[i] = sw[i + 2];
      }
      TSIF(w == 0, 28);
      __syncwarp();
      if (lane == 0) mbar_arrive(bars + 8 * B_KVD + ((res[8].x ^ res[9].x) & p.zero));
      mbar_wait(bars + 8 * B_KVD, 0);
      fft_tables_store(tab, sb, tw);
      mbar_wait(bars + 8 * B_LAST, 0);
#pragma unroll
      for (int i = 0; i < 10; i++) up[(128 * (i >> 1) + 32 * (i & 1)) * U_PITCH] = res[i];
      __syncwarp();
      if (lane == 0) mbar_arrive(bars + 8 * B_PREP);
      TSIF(w == 0 && !U_TMA, 5);
      mbar_wait(bars + 8 * (G_AFTER ? B_USIG : B_LAST), 0);
      prep_gate(p, sb, b, w, lane);
      __syncwarp();
      if (lane == 0) mbar_arrive(bars + 8 * B_GATE);
      TSIF(w == 0, 72);
      mbar_wait(bars + 8 * B_HB, 0);
      TSIF(w == 0, 2);
      const uint32_t ha = sb + U_BYTES + ((tw >> 3) * 16 + 8 + (tw & 7)) * 16;
      uint4 hv[5];
#pragma unroll
      for (int c = 0; c < 5; c++) hv[c] = lds128(ha + off_ch(c));
      __syncwarp();
#pragma unroll
      for (int c = 0; c < 5; c++) sts128((ha ^ 16) + off_ch(c), hv[c].x, hv[c].y, hv[c].z, hv[c].w);
      asm volatile("st.shared.v2.u32 [%0], {%1, %2};" ::"r"(sb + OFF_TT + 8 * tw), "r"(tt[0]), "r"(tt[1]) : "memory");
      if (tw < 5) asm volatile("st.shared.f32 [%0], %1;" ::"r"(sb + OFF_D + 4 * tw), "f"(bf_lo(dv) * 0.125f) : "memory");
      fence_async_smem();
      __syncwarp();
      if (lane == 0) mbar_arrive(bars + 8 * B_HA);
      TSIF(w == 0, 6);
    }

    FftConst fc;
    TSM(w == 0 && wg == 0, 104);
    mbar_wait(bars + 8 * B_HA, 0);
    fft_matrices(fc, sb, w, lane);
    TSM(w == 0 && wg == 0, 105);
    TSM(w == 0 && wg == 2, 124);
#pragma unroll 1
    for (uint32_t tasks = wg == 0 ? TASK0 : wg == 1 ? TASK1 : TASK2; tasks; tasks >>= 4) {
      const int c = (tasks & 7) - 1;
      conv_channel(fc, sb, c, wg, w, lane);
      if (lane == 0) mbar_arrive(bars + 8 * (B_YST + c));
      TSM(w == 0, 10 + c);
    }

    if (wg < 2) {
      const int g = lane >> 2;
      float acc[40];
#pragma unroll
      for (int i = 0; i < 40; i++) acc[i] = 0.f;
      const uint32_t da = desc_lo(sb + wg * 1024, 2048), db = desc_lo(sb, 2560);
      mbar_wait(bars + 8 * (O_RB == 2 ? B_ORB : B_ATTN), 0);
      if (PW2) mbar_wait(bars + 8 * B_FULL2, 0);
      mbar_wait(bars + 8 * B_CVD, 0);
      TSM(w == 0, 15 + wg);
#pragma unroll 1
      for (int j = 0; j < 8; j++) {
        mbar_wait(bars + 8 * (B_FULL2 + j), 0);
        TSM(w == 0 && wg == 0, 44 + (j < 4 ? j : j + 6));
        const uint32_t oa = da + (off_o(j) >> 4), ob = db + (off_w(j) >> 4);
        wg_fence();
#pragma unroll
        for (int k = 0; k < 5; k++) WgSST<80>::mma<HI_NONE, HI_SW32>(acc, oa + 256 * k, ob + 32 * k, 1);
        wg_commit();
        wg_wait<1>();
        if (j >= 1 && j <= Q_SLOT + 1 && lane == 0) mbar_arrive(bars + 8 * (B_EMPTY2 + j - 1));
      }
      TSIF(w == 0 && wg == 0, 113);
      const int tr = 64 * wg + 16 * w + (lane & 15);
      const uint32_t fm = sb + OFF_QS + tr * 128, fx = (lane >> 4) ^ (tr & 7), fq = sb + OFF_QS + tr * 160 + (lane >> 4) * 16;
      const uint32_t ft = sb + OFF_QT + tr * 32 + (((lane >> 4) ^ (tr >> 2)) & 1) * 16;
      const float g0 = __uint_as_float(lds32(sb + OFF_GATE + (64 * wg + 16 * w + g) * 4));
      const float g1 = __uint_as_float(lds32(sb + OFF_GATE + (64 * wg + 16 * w + 8 + g) * 4));
      const uint32_t ga = pack2(g0, g0), gb = pack2(g1, g1);
      const uint32_t na = pack2(1.f - g0, 1.f - g0), nb = pack2(1.f - g1, 1.f - g1);

      uint32_t qf[20];
      mbar_wait(bars + 8 * B_QF, 0);
      TSM(w == 0 && wg == 0, 99);
#pragma unroll
      for (int j = 0; j < 5; j++) ldsm4(qf + 4 * j, QBOX ? fq + 32 * j : j < 4 ? fm + ((fx ^ (2 * j)) << 4) : ft);
      if (FUSE_MIX) {
#pragma unroll
        for (int i = 0; i < 20; i++) {
          qf[i] = bmul((i & 1) ? gb : ga, qf[i]);
          asm volatile("" : "+r"(qf[i]));
        }
      }
      wg_wait<0>();
      pin<40>(acc);
      TSM(w == 0, 17 + wg);
      uint32_t pb[20];
#pragma unroll
      for (int j = 0; j < 10; j++) {
        pb[2 * j] = bmul(na, pack2(acc[4 * j], acc[4 * j + 1]));
        pb[2 * j + 1] = bmul(nb, pack2(acc[4 * j + 2], acc[4 * j + 3]));
        asm volatile("" : "+r"(pb[2 * j]), "+r"(pb[2 * j + 1]));
      }
      const uint32_t ya = sb + OFF_YT + wg * 10240 + ((lane >> 4) * 8 + (lane & 7)) * 128 +
                          (((2 * w + (((lane >> 3) & 1) ^ wg)) ^ (lane & 7)) << 4);
      mbar_wait(bars + 8 * B_YFULL, 0);
      TSM(w == 0 && wg == 0, 19);
#pragma unroll
      for (int j = 0; j < 5; j++) {
        uint32_t y[4];
        ldsm4t(y, ya + 2048 * j);
#pragma unroll
        for (int i = 0; i < 4; i++)
          qf[4 * j + i] = FUSE_MIX ? bfma(qf[4 * j + i], y[i], pb[4 * j + i]) : badd(bmul((i & 1) ? gb : ga, bmul(qf[4 * j + i], y[i])), pb[4 * j + i]);
      }
#pragma unroll
      for (int j = 0; j < 5; j++) stsm4(QBOX ? fq + 32 * j : j < 4 ? fm + ((fx ^ (2 * j)) << 4) : ft, qf + 4 * j);
      fence_async_smem();
      __syncwarp();
      if (lane == 0) {
        const int row = 64 * wg + 16 * w;
        asm volatile("cp.async.bulk.tensor.2d.global.shared::cta.bulk_group [%0, {%2, %3}], [%1];"
                     ::"l"(&m.om), "r"(sb + OFF_QS + row * (QBOX ? 160 : 128)), "r"(80 * hg), "r"(128 * r + row) : "memory");
        if (!QBOX) asm volatile("cp.async.bulk.tensor.2d.global.shared::cta.bulk_group [%0, {%2, %3}], [%1];"
                     ::"l"(&m.ot), "r"(sb + OFF_QT + row * 32), "r"(80 * hg + 64), "r"(128 * r + row) : "memory");
        asm volatile("cp.async.bulk.commit_group;\ncp.async.bulk.wait_group.read 0;" ::: "memory");
      }
      TSM(w == 0 || w == 3, 40 + 2 * wg + (w & 1));
      if (ENDBAR) asm volatile("bar.sync 15, 256;" ::: "memory");
    }
  }
}

typedef CUresult (*EncodeFn)(CUtensorMap*, CUtensorMapDataType, cuuint32_t, void*, const cuuint64_t*, const cuuint64_t*,
                             const cuuint32_t*, const cuuint32_t*, CUtensorMapInterleave, CUtensorMapSwizzle,
                             CUtensorMapL2promotion, CUtensorMapFloatOOBfill);

void encode(EncodeFn fn, CUtensorMap* tm, const void* base, int rank, const cuuint64_t* dims, const cuuint64_t* strides,
            const cuuint32_t* box, CUtensorMapSwizzle swz) {
  const cuuint32_t ones[3] = {1, 1, 1};
  fn(tm, CU_TENSOR_MAP_DATA_TYPE_BFLOAT16, rank, const_cast<void*>(base), dims, strides, box, ones,
     CU_TENSOR_MAP_INTERLEAVE_NONE, swz, CU_TENSOR_MAP_L2_PROMOTION_L2_128B, CU_TENSOR_MAP_FLOAT_OOB_FILL_NONE);
}

}

extern "C" void kernel_launch(void* const* d_in, const int* in_sizes, int n_in, void* d_out, int out_size) {
  (void)in_sizes; (void)n_in; (void)out_size;
  Params p;
  p.q = (const __nv_bfloat16*)d_in[0];
  p.k = (const __nv_bfloat16*)d_in[1];
  p.v = (const __nv_bfloat16*)d_in[2];
  p.shift_k = (const __nv_bfloat16*)d_in[3];
  p.ssm_k = (const __nv_bfloat16*)d_in[4];
  p.ssm_D = (const __nv_bfloat16*)d_in[5];
  p.wqkv = (const __nv_bfloat16*)d_in[7];
  p.wo = (const __nv_bfloat16*)d_in[8];
  p.gate_w = (const __nv_bfloat16*)d_in[9];
  p.out = (__nv_bfloat16*)d_out;
  p.zero = 0;

  static EncodeFn fn = nullptr;
  static void *yaddr = nullptr, *uaddr = nullptr;
  if (!fn) {
    cudaDriverEntryPointQueryResult qr;
    void* f = nullptr;
    cudaGetDriverEntryPoint("cuTensorMapEncodeTiled", &f, cudaEnableDefault, &qr);
    fn = (EncodeFn)f;
    cudaGetSymbolAddress(&yaddr, g_Y);
    cudaGetSymbolAddress(&uaddr, g_U);
    cudaFuncSetAttribute(fused_kernel, cudaFuncAttributeMaxDynamicSharedMemorySize, SMEM_BYTES);
  }
  Maps m;
  {
    const cuuint64_t dims[3] = {640, 1024, 2}, st[2] = {2560, 1280};
    const cuuint32_t box[3] = {64, 64, 2};
    encode(fn, &m.x, p.q, 3, dims, st, box, CU_TENSOR_MAP_SWIZZLE_128B);
  }
  {
    const cuuint64_t dims[3] = {640, 640, 3}, st[2] = {3840, 1280};
    const cuuint32_t box[3] = {64, 64, 3}, boxt[3] = {16, 64, 3};
    encode(fn, &m.wm, p.wqkv, 3, dims, st, box, CU_TENSOR_MAP_SWIZZLE_128B);
    encode(fn, &m.wt, p.wqkv, 3, dims, st, boxt, CU_TENSOR_MAP_SWIZZLE_32B);
  }
  {
    const cuuint64_t dims[3] = {64, 2048, 10}, st[2] = {1280, 128};
    const cuuint32_t boxk[3] = {64, 35, 1}, boxv[3] = {64, 32, 1};
    encode(fn, &m.k, p.k, 3, dims, st, boxk, CU_TENSOR_MAP_SWIZZLE_128B);
    encode(fn, &m.v, p.v, 3, dims, st, boxv, CU_TENSOR_MAP_SWIZZLE_128B);
  }
  {
    const cuuint64_t dims[3] = {16, 640, 40}, st[2] = {1280, 32};
    const cuuint32_t box[3] = {16, 40, 5};
    encode(fn, &m.wo, p.wo, 3, dims, st, box, CU_TENSOR_MAP_SWIZZLE_32B);
  }
  {
    const cuuint64_t dims[2] = {2048, 640}, st[1] = {Y_PITCH * 16};
    const cuuint32_t box[2] = {64, 80};
    encode(fn, &m.y, yaddr, 2, dims, st, box, CU_TENSOR_MAP_SWIZZLE_128B);
    const cuuint64_t stu[1] = {U_PITCH * 16};
    const cuuint32_t boxu[2] = {32, 64};
    encode(fn, &m.u, uaddr, 2, dims, stu, boxu, CU_TENSOR_MAP_SWIZZLE_NONE);
  }
  {
    const cuuint64_t dims[2] = {640, 2048}, st[1] = {1280};
    const cuuint32_t bqm[2] = {QBOX ? 80 : 64, 128}, bqt[2] = {16, 128}, bom[2] = {QBOX ? 80 : 64, 16}, bot[2] = {16, 16};
    encode(fn, &m.qm, p.q, 2, dims, st, bqm, QBOX ? CU_TENSOR_MAP_SWIZZLE_NONE : CU_TENSOR_MAP_SWIZZLE_128B);
    encode(fn, &m.qt, p.q, 2, dims, st, bqt, CU_TENSOR_MAP_SWIZZLE_32B);
    encode(fn, &m.om, p.out, 2, dims, st, bom, QBOX ? CU_TENSOR_MAP_SWIZZLE_NONE : CU_TENSOR_MAP_SWIZZLE_128B);
    encode(fn, &m.ot, p.out, 2, dims, st, bot, CU_TENSOR_MAP_SWIZZLE_32B);
  }
  fused_kernel<<<NCTA, NTHR, SMEM_BYTES>>>(m, p);
}
```

```cpp
#include <cuda.h>
#include <cuda_bf16.h>
#include <cuda_runtime.h>
#include <stdint.h>

namespace {

constexpr int SEQ = 2048, DIM = 640, NCTA = 128, NTHR = 512;

#define TRIG_KB 9
#define KV_KB 2
#define DEV_EXIT 0
#define ATT_GATE 0
#define G_AFTER 0
#define FENCE_LO 0
#define FENCE_HI 0
#define PW1 2
#define PW2 1
#define ENDBAR 0
#define PAD_KB 0
#define Y_ALIAS 1
#define NOMB 0
#define SRC_ROT 0
#define WAIT_NS 0
#define WB_TRIG B_USIG
#define G_POS 0
#define TAILF 1
#define T_ISSUE 384
#define T_PF 416
#define T_INIT 448
#define ATT_MERGE 0
#define BMAP 1
#define PRE2 1
#define KV_MIX 0
#define O_DEFER 0
#define TASK0 0x3
#define TASK1 0x52
#define TASK2 0x41
#define HALO_FIRST 1
#define PREV_EARLY 0
#define Y_RB 2
#define O_RB 2
#define O_EAGER 1
#define OP_TRIG B_ATTN
#define FUSE_MIX 1
#define Q_EARLY 1
#define U_TRIM 1
#define Q_SLOT 3
#define G_TMA 1
#define W_RB 1
#define WPF B_S3
#define WPF_LIN 1
#define QBOX 0
#define T0_DELAY 200
#define ACQ 0
#define U_TMA 0
#define U_GATE 0
#define RF_GATE 0
#define WO_TRIG B_WST
#define WL_TRIG B_WOP
#define WO_GATE 4

constexpr uint32_t STAGE_BYTES = 47104, ST_W = 16384, ST_WT = 40960;
constexpr uint32_t O_BYTES = 20480, WO_BYTES = 12800;
constexpr uint32_t OFF_OA = 0;
constexpr uint32_t OFF_QS = Q_SLOT * O_BYTES, OFF_QT = OFF_QS + 16384;
constexpr uint32_t OFF_WC = 81920;
constexpr uint32_t OFF_WA = 94720;
constexpr uint32_t OFF_GATE = 145920;
constexpr uint32_t OFF_TT = 146432;
constexpr uint32_t OFF_KVX = 148480;
constexpr uint32_t OFF_CH3 = 163840;
constexpr uint32_t CH_BYTES = 12288, U_BYTES = 4096;
constexpr uint32_t OFF_FT = 225280, OFF_GT = 229376;
constexpr uint32_t OFF_CH0 = 188416;
constexpr uint32_t OFF_KVS = OFF_CH0, KVS_V = 4480, KVS_BYTES = 8576;
constexpr uint32_t OFF_WS = OFF_WA;
__device__ __forceinline__ uint32_t off_us(int s) { return OFF_CH0 + 4096 * ((0x65320 >> (4 * s)) & 7); }
constexpr uint32_t OFF_YT = 163840;
constexpr uint32_t OFF_BAR = 231936;
constexpr uint32_t SMEM_BYTES = OFF_BAR + 512;

enum : uint32_t {
  B_FULL1 = 0, B_EMPTY1 = 4, B_S3 = 7, B_FULL2 = 52, B_EMPTY2 = 13, B_U = 8, B_GATE = 12, B_HA = 19, B_HB = 20,
  B_ATTN = 21, B_C34 = 22, B_YRB = 23, B_YFULL = 24, B_EPOCH = 25, B_PREP = 26, B_P1 = 27, B_LAST = 28,
  B_E3 = 29, B_OSIG = 30, B_WOP = 31, B_USIG = 32, B_WST = 33, B_KV = 34, B_KVD = 39, B_QF = 17, B_ATT2 = 18, B_YST = 40,
  B_ORB = 45, B_F0 = 33 + 15, B_CVD = 33 + 14, B_US = 45, B_YSIG = 50
};
constexpr uint32_t OFF_EPOCH = OFF_BAR + 8 * 51, OFF_D = OFF_BAR + 8 * 60;
__device__ __forceinline__ uint32_t off_o(int j) { return j < 4 ? OFF_OA + j * O_BYTES : j < 6 ? OFF_CH0 + (j - 4) * O_BYTES : OFF_OA + (j - 6) * O_BYTES; }
__device__ __forceinline__ uint32_t off_w(int j) { return j < 4 ? OFF_WA + j * WO_BYTES : j == 4 ? OFF_KVX : j == 5 ? OFF_WC : OFF_WA + (j - 6) * WO_BYTES; }
__device__ __forceinline__ int step_src(int hg, int j) {
  if (SRC_ROT == 2) {
    const int pos = (0x37621540 >> (4 * hg)) & 7;
    return j == 0 ? hg : (0x65217430 >> (4 * (j <= pos ? j - 1 : j))) & 7;
  }
  return SRC_ROT ? (hg + j) & 7 : j == 0 ? hg : j <= hg ? j - 1 : j;
}
__device__ __forceinline__ bool tail_first(int hg) { return TAILF && (hg & 3) == 3; }
__device__ __forceinline__ uint32_t off_ch(int c) { return (c < 3 ? OFF_CH0 : OFF_CH3 - 3 * CH_BYTES) + c * CH_BYTES; }

#define U_PITCH 264
__device__ __align__(1024) uint4 g_U[DIM * U_PITCH];
__device__ uint4 g_O[NCTA * 1280];
#define g_Y g_U
constexpr int Y_PITCH = U_PITCH;
__device__ uint4 g_WO[64 * 800];
__device__ uint4 g_halo[NCTA * 2 * 7 * 32];
__device__ __align__(128) float g_gate[SEQ + PAD_KB * 256];
__device__ unsigned g_cnt[32 * (1 + 2 * 16 + 8 + NCTA)];
constexpr int C_LAUNCH = 0, C_PREP = 32, C_Y = 32 * 17, C_W = 32 * 33, C_O = 32 * 41;

#define TSM(cond, slot) do { } while (0)
#define TSIF(cond, slot) do { if (__LINE__ >= FENCE_LO && __LINE__ < FENCE_HI) sched_fence(); } while (0)
__device__ __forceinline__ void sched_fence() {
  asm volatile("{\n.reg .pred p;\n.reg .u32 c;\nmov.u32 c, %%clock;\nsetp.eq.u32 p, c, 0;\n@p st.shared.u32 [%0], c;\n}"
               ::"r"(1024 + OFF_EPOCH + 4) : "memory");
}
#define TS(slot) TSIF(true, slot)

struct Params {
  const __nv_bfloat16 *q, *k, *v, *shift_k, *ssm_k, *ssm_D, *wqkv, *wo, *gate_w;
  __nv_bfloat16* out;
  uint32_t zero;
};

#define POLL_NS 0
constexpr int SPIN_LIMIT = 1 << 17;

__device__ __forceinline__ void mbar_init(uint32_t bar, uint32_t count) {
  asm volatile("mbarrier.init.shared::cta.b64 [%0], %1;" ::"r"(bar), "r"(count) : "memory");
}
__device__ __forceinline__ void mbar_expect_tx(uint32_t bar, uint32_t bytes) {
  asm volatile("mbarrier.arrive.expect_tx.shared::cta.b64 _, [%0], %1;" ::"r"(bar), "r"(bytes) : "memory");
}
__device__ __forceinline__ void mbar_arrive(uint32_t bar) {
  asm volatile("mbarrier.arrive.shared::cta.b64 _, [%0];" ::"r"(bar) : "memory");
}
__device__ __forceinline__ void mbar_wait(uint32_t bar, uint32_t parity) {
  uint32_t ok;
  int spins = 0;
  do {
    if (WAIT_NS)
      asm volatile("{\n.reg .pred p;\nmbarrier.try_wait.parity.shared::cta.b64 p, [%1], %2, %3;\nselp.b32 %0, 1, 0, p;\n}"
                   : "=r"(ok) : "r"(bar), "r"(parity), "r"(WAIT_NS) : "memory");
    else
      asm volatile("{\n.reg .pred p;\nmbarrier.try_wait.parity.shared::cta.b64 p, [%1], %2;\nselp.b32 %0, 1, 0, p;\n}"
                   : "=r"(ok) : "r"(bar), "r"(parity) : "memory");
    if (++spins > SPIN_LIMIT) break;
  } while (!ok);
}
__device__ __forceinline__ unsigned flag_read(const unsigned* p) {
  unsigned v;
  asm volatile("ld.relaxed.gpu.global.u32 %0, [%1];" : "=r"(v) : "l"(p) : "memory");
  return v;
}
__device__ __forceinline__ void flag_poll(const unsigned* p, unsigned target) {
  unsigned v;
  int spins = 0;
  do {
    if (POLL_NS && spins) __nanosleep(POLL_NS);
    asm volatile("ld.relaxed.gpu.global.u32 %0, [%1];" : "=r"(v) : "l"(p) : "memory");
    if (++spins > SPIN_LIMIT) break;
  } while ((int)(v - target) < 0);
}
__device__ __forceinline__ void flag_wait(const unsigned* p, unsigned target) {
  flag_poll(p, target);
  if (ACQ) asm volatile("fence.acquire.gpu;\nfence.proxy.async.global;" ::: "memory");
}
__device__ __forceinline__ void flag_signal(unsigned* p, int n, int lane) {
  if (lane == 0) asm volatile("fence.release.gpu;" ::: "memory");
  __syncwarp();
  if (lane < n) asm volatile("red.relaxed.gpu.global.add.u32 [%0], 1;" ::"l"(p + 32 * lane) : "memory");
}
__device__ __forceinline__ void flag_bump(unsigned* p) {
  asm volatile("red.relaxed.gpu.global.add.u32 [%0], 1;" ::"l"(p) : "memory");
}
__device__ __forceinline__ void fence_async_smem() { asm volatile("fence.proxy.async.shared::cta;" ::: "memory"); }
__device__ __forceinline__ void wg_sync(int id) { asm volatile("bar.sync %0, 128;" ::"r"(id) : "memory"); }

__device__ __forceinline__ void tma_2d(uint32_t dst, const CUtensorMap* tm, int c0, int c1, uint32_t bar) {
  asm volatile("cp.async.bulk.tensor.2d.shared::cluster.global.mbarrier::complete_tx::bytes [%0], [%1, {%3, %4}], [%2];"
               ::"r"(dst), "l"(tm), "r"(bar), "r"(c0), "r"(c1) : "memory");
}
__device__ __forceinline__ void tma_3d(uint32_t dst, const CUtensorMap* tm, int c0, int c1, int c2, uint32_t bar) {
  asm volatile("cp.async.bulk.tensor.3d.shared::cluster.global.mbarrier::complete_tx::bytes [%0], [%1, {%3, %4, %5}], [%2];"
               ::"r"(dst), "l"(tm), "r"(bar), "r"(c0), "r"(c1), "r"(c2) : "memory");
}
__device__ __forceinline__ void bulk_load(uint32_t dst, const void* src, uint32_t bytes, uint32_t bar) {
  asm volatile("cp.async.bulk.shared::cluster.global.mbarrier::complete_tx::bytes [%0], [%1], %2, [%3];"
               ::"r"(dst), "l"(src), "r"(bytes), "r"(bar) : "memory");
}
__device__ __forceinline__ void tm_prefetch(const CUtensorMap* tm) {
  asm volatile("prefetch.tensormap [%0];" ::"l"(tm) : "memory");
}

__device__ __forceinline__ void wg_fence() { asm volatile("wgmma.fence.sync.aligned;" ::: "memory"); }
__device__ __forceinline__ void wg_commit() { asm volatile("wgmma.commit_group.sync.aligned;" ::: "memory"); }
template <int N> __device__ __forceinline__ void wg_wait() { asm volatile("wgmma.wait_group.sync.aligned %0;" ::"n"(N) : "memory"); }
__device__ __forceinline__ uint32_t desc_lo(uint32_t addr, uint32_t lbo) { return ((addr & 0x3FFFF) >> 4) | ((lbo >> 4) << 16); }
constexpr uint32_t desc_hi(uint32_t sbo, uint32_t swz) { return (sbo >> 4) | (swz << 30); }
constexpr uint32_t HI_SW128 = desc_hi(1024, 1), HI_SW64 = desc_hi(512, 2), HI_SW32 = desc_hi(256, 3), HI_NONE = desc_hi(128, 0);
template <int N> __device__ __forceinline__ void pin(float* d) {
#pragma unroll
  for (int i = 0; i < N; i++) asm volatile("" : "+f"(d[i])::"memory");
}

__device__ __forceinline__ uint32_t lds32(uint32_t a) {
  uint32_t v;
  asm volatile("ld.volatile.shared.u32 %0, [%1];" : "=r"(v) : "r"(a) : "memory");
  return v;
}
__device__ __forceinline__ uint4 ldg128(const void* a) {
  uint4 v;
  asm volatile("ld.global.nc.v4.u32 {%0, %1, %2, %3}, [%4];" : "=r"(v.x), "=r"(v.y), "=r"(v.z), "=r"(v.w) : "l"(a) : "memory");
  return v;
}
__device__ __forceinline__ uint2 ldg64(const void* a) {
  uint2 v;
  asm volatile("ld.global.nc.v2.u32 {%0, %1}, [%2];" : "=r"(v.x), "=r"(v.y) : "l"(a) : "memory");
  return v;
}
__device__ __forceinline__ void ldsm4(uint32_t* r, uint32_t a) {
  asm volatile("ldmatrix.sync.aligned.m8n8.x4.shared.b16 {%0, %1, %2, %3}, [%4];"
               : "=r"(r[0]), "=r"(r[1]), "=r"(r[2]), "=r"(r[3]) : "r"(a) : "memory");
}
__device__ __forceinline__ void ldsm4t(uint32_t* r, uint32_t a) {
  asm volatile("ldmatrix.sync.aligned.m8n8.x4.trans.shared.b16 {%0, %1, %2, %3}, [%4];"
               : "=r"(r[0]), "=r"(r[1]), "=r"(r[2]), "=r"(r[3]) : "r"(a) : "memory");
}
__device__ __forceinline__ uint2 lds64(uint32_t a) {
  uint2 v;
  asm volatile("ld.shared.v2.u32 {%0, %1}, [%2];" : "=r"(v.x), "=r"(v.y) : "r"(a) : "memory");
  return v;
}
__device__ __forceinline__ uint4 lds128(uint32_t a) {
  uint4 v;
  asm volatile("ld.shared.v4.u32 {%0, %1, %2, %3}, [%4];" : "=r"(v.x), "=r"(v.y), "=r"(v.z), "=r"(v.w) : "r"(a) : "memory");
  return v;
}
__device__ __forceinline__ void sts128(uint32_t a, uint32_t x, uint32_t y, uint32_t z, uint32_t w) {
  asm volatile("st.shared.v4.u32 [%0], {%1, %2, %3, %4};" ::"r"(a), "r"(x), "r"(y), "r"(z), "r"(w) : "memory");
}
__device__ __forceinline__ void stsm4(uint32_t a, const uint32_t* r) {
  asm volatile("stmatrix.sync.aligned.m8n8.x4.shared.b16 [%0], {%1, %2, %3, %4};" ::"r"(a), "r"(r[0]), "r"(r[1]), "r"(r[2]), "r"(r[3]) : "memory");
}
__device__ __forceinline__ void stsm4t(uint32_t a, const uint32_t* r) {
  asm volatile("stmatrix.sync.aligned.m8n8.x4.trans.shared.b16 [%0], {%1, %2, %3, %4};" ::"r"(a), "r"(r[0]), "r"(r[1]), "r"(r[2]), "r"(r[3]) : "memory");
}
__device__ __forceinline__ uint32_t pack2(float lo, float hi) {
  uint32_t r;
  asm("cvt.rn.bf16x2.f32 %0, %1, %2;" : "=r"(r) : "f"(hi), "f"(lo));
  return r;
}
__device__ __forceinline__ uint32_t movm(uint32_t a) {
  uint32_t d;
  asm volatile("movmatrix.sync.aligned.m8n8.trans.b16 %0, %1;" : "=r"(d) : "r"(a));
  return d;
}
__device__ __forceinline__ uint32_t bmul(uint32_t a, uint32_t b) {
  uint32_t d;
  asm("mul.rn.bf16x2 %0, %1, %2;" : "=r"(d) : "r"(a), "r"(b));
  return d;
}
__device__ __forceinline__ uint32_t badd(uint32_t a, uint32_t b) {
  uint32_t d;
  asm("add.rn.bf16x2 %0, %1, %2;" : "=r"(d) : "r"(a), "r"(b));
  return d;
}
__device__ __forceinline__ uint32_t bfma(uint32_t a, uint32_t b, uint32_t c) {
  uint32_t d;
  asm("fma.rn.bf16x2 %0, %1, %2, %3;" : "=r"(d) : "r"(a), "r"(b), "r"(c));
  return d;
}
__device__ __forceinline__ float bf_lo(uint32_t x) { return __uint_as_float(x << 16); }
__device__ __forceinline__ float bf_hi(uint32_t x) { return __uint_as_float(x & 0xFFFF0000u); }
__device__ __forceinline__ float ex2(float x) {
  float y;
  asm("ex2.approx.ftz.f32 %0, %1;" : "=f"(y) : "f"(x));
  return y;
}
__device__ __forceinline__ float rcp(float x) {
  float y;
  asm("rcp.approx.ftz.f32 %0, %1;" : "=f"(y) : "f"(x));
  return y;
}
__device__ __forceinline__ void mma16816(float* d, uint32_t a0, uint32_t a1, uint32_t a2, uint32_t a3, uint32_t b0, uint32_t b1) {
  asm volatile("mma.sync.aligned.m16n8k16.row.col.f32.bf16.bf16.f32 {%0, %1, %2, %3}, {%4, %5, %6, %7}, {%8, %9}, {%0, %1, %2, %3};"
               : "+f"(d[0]), "+f"(d[1]), "+f"(d[2]), "+f"(d[3])
               : "r"(a0), "r"(a1), "r"(a2), "r"(a3), "r"(b0), "r"(b1));
}
__device__ __forceinline__ void mma1688(float* d, uint32_t a0, uint32_t a1, uint32_t b0) {
  asm volatile("mma.sync.aligned.m16n8k8.row.col.f32.bf16.bf16.f32 {%0, %1, %2, %3}, {%4, %5}, {%6}, {%0, %1, %2, %3};"
               : "+f"(d[0]), "+f"(d[1]), "+f"(d[2]), "+f"(d[3])
               : "r"(a0), "r"(a1), "r"(b0));
}

template <int N> struct WgRS;
template <int N> struct WgSST;
template <> struct WgRS<32> {
  template <uint32_t HB>
  static __device__ __forceinline__ void mma(float* d, const uint32_t* a, uint32_t db) {
    asm volatile("{\n.reg .pred p;\n.reg .b64 db;\nsetp.ne.b32 p, %22, 0;\n"
      "mov.b64 db, {%20, %21};\n"
      "wgmma.mma_async.sync.aligned.m64n32k16.f32.bf16.bf16 {"
      "%0, %1, %2, %3, %4, %5, %6, %7, %8, %9, %10, %11, %12, %13, %14, %15"
      "}, {%16, %17, %18, %19}, db, p, 1, 1, 1;\n}\n"
      : "+f"(d[0]), "+f"(d[1]), "+f"(d[2]), "+f"(d[3]), "+f"(d[4]), "+f"(d[5]), "+f"(d[6]), "+f"(d[7]),
        "+f"(d[8]), "+f"(d[9]), "+f"(d[10]), "+f"(d[11]), "+f"(d[12]), "+f"(d[13]), "+f"(d[14]), "+f"(d[15])
      : "r"(a[0]), "r"(a[1]), "r"(a[2]), "r"(a[3]), "r"(db), "n"(HB), "n"(1));
  }
  template <uint32_t HB>
  static __device__ __forceinline__ void set(float* d, const uint32_t* a, uint32_t db) {
    asm volatile("{\n.reg .pred p;\n.reg .b64 db;\nsetp.ne.b32 p, %22, 0;\n"
      "mov.b64 db, {%20, %21};\n"
      "wgmma.mma_async.sync.aligned.m64n32k16.f32.bf16.bf16 {"
      "%0, %1, %2, %3, %4, %5, %6, %7, %8, %9, %10, %11, %12, %13, %14, %15"
      "}, {%16, %17, %18, %19}, db, p, 1, 1, 1;\n}\n"
      : "=f"(d[0]), "=f"(d[1]), "=f"(d[2]), "=f"(d[3]), "=f"(d[4]), "=f"(d[5]), "=f"(d[6]), "=f"(d[7]),
        "=f"(d[8]), "=f"(d[9]), "=f"(d[10]), "=f"(d[11]), "=f"(d[12]), "=f"(d[13]), "=f"(d[14]), "=f"(d[15])
      : "r"(a[0]), "r"(a[1]), "r"(a[2]), "r"(a[3]), "r"(db), "n"(HB), "n"(0));
  }
};
template <> struct WgRS<64> {
  template <uint32_t HB>
  static __device__ __forceinline__ void mma(float* d, const uint32_t* a, uint32_t db) {
    asm volatile("{\n.reg .pred p;\n.reg .b64 db;\nsetp.ne.b32 p, %38, 0;\n"
      "mov.b64 db, {%36, %37};\n"
      "wgmma.mma_async.sync.aligned.m64n64k16.f32.bf16.bf16 {"
      "%0, %1, %2, %3, %4, %5, %6, %7, %8, %9, %10, %11, %12, %13, %14, %15, "
      "%16, %17, %18, %19, %20, %21, %22, %23, %24, %25, %26, %27, %28, %29, %30, %31"
      "}, {%32, %33, %34, %35}, db, p, 1, 1, 1;\n}\n"
      : "+f"(d[0]), "+f"(d[1]), "+f"(d[2]), "+f"(d[3]), "+f"(d[4]), "+f"(d[5]), "+f"(d[6]), "+f"(d[7]),
        "+f"(d[8]), "+f"(d[9]), "+f"(d[10]), "+f"(d[11]), "+f"(d[12]), "+f"(d[13]), "+f"(d[14]), "+f"(d[15]),
        "+f"(d[16]), "+f"(d[17]), "+f"(d[18]), "+f"(d[19]), "+f"(d[20]), "+f"(d[21]), "+f"(d[22]), "+f"(d[23]),
        "+f"(d[24]), "+f"(d[25]), "+f"(d[26]), "+f"(d[27]), "+f"(d[28]), "+f"(d[29]), "+f"(d[30]), "+f"(d[31])
      : "r"(a[0]), "r"(a[1]), "r"(a[2]), "r"(a[3]), "r"(db), "n"(HB), "n"(1));
  }
  template <uint32_t HB>
  static __device__ __forceinline__ void set(float* d, const uint32_t* a, uint32_t db) {
    asm volatile("{\n.reg .pred p;\n.reg .b64 db;\nsetp.ne.b32 p, %38, 0;\n"
      "mov.b64 db, {%36, %37};\n"
      "wgmma.mma_async.sync.aligned.m64n64k16.f32.bf16.bf16 {"
      "%0, %1, %2, %3, %4, %5, %6, %7, %8, %9, %10, %11, %12, %13, %14, %15, "
      "%16, %17, %18, %19, %20, %21, %22, %23, %24, %25, %26, %27, %28, %29, %30, %31"
      "}, {%32, %33, %34, %35}, db, p, 1, 1, 1;\n}\n"
      : "=f"(d[0]), "=f"(d[1]), "=f"(d[2]), "=f"(d[3]), "=f"(d[4]), "=f"(d[5]), "=f"(d[6]), "=f"(d[7]),
        "=f"(d[8]), "=f"(d[9]), "=f"(d[10]), "=f"(d[11]), "=f"(d[12]), "=f"(d[13]), "=f"(d[14]), "=f"(d[15]),
        "=f"(d[16]), "=f"(d[17]), "=f"(d[18]), "=f"(d[19]), "=f"(d[20]), "=f"(d[21]), "=f"(d[22]), "=f"(d[23]),
        "=f"(d[24]), "=f"(d[25]), "=f"(d[26]), "=f"(d[27]), "=f"(d[28]), "=f"(d[29]), "=f"(d[30]), "=f"(d[31])
      : "r"(a[0]), "r"(a[1]), "r"(a[2]), "r"(a[3]), "r"(db), "n"(HB), "n"(0));
  }
};
template <> struct WgSST<48> {
  template <uint32_t HA, uint32_t HB>
  static __device__ __forceinline__ void mma(float* d, uint32_t da, uint32_t db, int sc) {
    asm volatile("{\n.reg .pred p;\n.reg .b64 da, db;\nsetp.ne.b32 p, %28, 0;\n"
      "mov.b64 da, {%24, %25};\nmov.b64 db, {%26, %27};\n"
      "wgmma.mma_async.sync.aligned.m64n48k16.f32.bf16.bf16 {"
      "%0, %1, %2, %3, %4, %5, %6, %7, %8, %9, %10, %11, %12, %13, %14, %15, "
      "%16, %17, %18, %19, %20, %21, %22, %23"
      "}, da, db, p, 1, 1, 0, 1;\n}\n"
      : "+f"(d[0]), "+f"(d[1]), "+f"(d[2]), "+f"(d[3]), "+f"(d[4]), "+f"(d[5]), "+f"(d[6]), "+f"(d[7]),
        "+f"(d[8]), "+f"(d[9]), "+f"(d[10]), "+f"(d[11]), "+f"(d[12]), "+f"(d[13]), "+f"(d[14]), "+f"(d[15]),
        "+f"(d[16]), "+f"(d[17]), "+f"(d[18]), "+f"(d[19]), "+f"(d[20]), "+f"(d[21]), "+f"(d[22]), "+f"(d[23])
      : "r"(da), "n"(HA), "r"(db), "n"(HB), "r"(sc));
  }
};
template <> struct WgSST<80> {
  template <uint32_t HA, uint32_t HB>
  static __device__ __forceinline__ void mma(float* d, uint32_t da, uint32_t db, int sc) {
    asm volatile("{\n.reg .pred p;\n.reg .b64 da, db;\nsetp.ne.b32 p, %44, 0;\n"
      "mov.b64 da, {%40, %41};\nmov.b64 db, {%42, %43};\n"
      "wgmma.mma_async.sync.aligned.m64n80k16.f32.bf16.bf16 {"
      "%0, %1, %2, %3, %4, %5, %6, %7, %8, %9, %10, %11, %12, %13, %14, %15, "
      "%16, %17, %18, %19, %20, %21, %22, %23, %24, %25, %26, %27, %28, %29, %30, %31, "
      "%32, %33, %34, %35, %36, %37, %38, %39"
      "}, da, db, p, 1, 1, 0, 1;\n}\n"
      : "+f"(d[0]), "+f"(d[1]), "+f"(d[2]), "+f"(d[3]), "+f"(d[4]), "+f"(d[5]), "+f"(d[6]), "+f"(d[7]),
        "+f"(d[8]), "+f"(d[9]), "+f"(d[10]), "+f"(d[11]), "+f"(d[12]), "+f"(d[13]), "+f"(d[14]), "+f"(d[15]),
        "+f"(d[16]), "+f"(d[17]), "+f"(d[18]), "+f"(d[19]), "+f"(d[20]), "+f"(d[21]), "+f"(d[22]), "+f"(d[23]),
        "+f"(d[24]), "+f"(d[25]), "+f"(d[26]), "+f"(d[27]), "+f"(d[28]), "+f"(d[29]), "+f"(d[30]), "+f"(d[31]),
        "+f"(d[32]), "+f"(d[33]), "+f"(d[34]), "+f"(d[35]), "+f"(d[36]), "+f"(d[37]), "+f"(d[38]), "+f"(d[39])
      : "r"(da), "n"(HA), "r"(db), "n"(HB), "r"(sc));
  }
};
template <> struct WgSST<192> {
  template <uint32_t HA, uint32_t HB>
  static __device__ __forceinline__ void mma(float* d, uint32_t da, uint32_t db, int sc) {
    asm volatile("{\n.reg .pred p;\n.reg .b64 da, db;\nsetp.ne.b32 p, %100, 0;\n"
      "mov.b64 da, {%96, %97};\nmov.b64 db, {%98, %99};\n"
      "wgmma.mma_async.sync.aligned.m64n192k16.f32.bf16.bf16 {"
      "%0, %1, %2, %3, %4, %5, %6, %7, %8, %9, %10, %11, %12, %13, %14, %15, "
      "%16, %17, %18, %19, %20, %21, %22, %23, %24, %25, %26, %27, %28, %29, %30, %31, "
      "%32, %33, %34, %35, %36, %37, %38, %39, %40, %41, %42, %43, %44, %45, %46, %47, "
      "%48, %49, %50, %51, %52, %53, %54, %55, %56, %57, %58, %59, %60, %61, %62, %63, "
      "%64, %65, %66, %67, %68, %69, %70, %71, %72, %73, %74, %75, %76, %77, %78, %79, "
      "%80, %81, %82, %83, %84, %85, %86, %87, %88, %89, %90, %91, %92, %93, %94, %95"
      "}, da, db, p, 1, 1, 0, 1;\n}\n"
      : "+f"(d[0]), "+f"(d[1]), "+f"(d[2]), "+f"(d[3]), "+f"(d[4]), "+f"(d[5]), "+f"(d[6]), "+f"(d[7]),
        "+f"(d[8]), "+f"(d[9]), "+f"(d[10]), "+f"(d[11]), "+f"(d[12]), "+f"(d[13]), "+f"(d[14]), "+f"(d[15]),
        "+f"(d[16]), "+f"(d[17]), "+f"(d[18]), "+f"(d[19]), "+f"(d[20]), "+f"(d[21]), "+f"(d[22]), "+f"(d[23]),
        "+f"(d[24]), "+f"(d[25]), "+f"(d[26]), "+f"(d[27]), "+f"(d[28]), "+f"(d[29]), "+f"(d[30]), "+f"(d[31]),
        "+f"(d[32]), "+f"(d[33]), "+f"(d[34]), "+f"(d[35]), "+f"(d[36]), "+f"(d[37]), "+f"(d[38]), "+f"(d[39]),
        "+f"(d[40]), "+f"(d[41]), "+f"(d[42]), "+f"(d[43]), "+f"(d[44]), "+f"(d[45]), "+f"(d[46]), "+f"(d[47]),
        "+f"(d[48]), "+f"(d[49]), "+f"(d[50]), "+f"(d[51]), "+f"(d[52]), "+f"(d[53]), "+f"(d[54]), "+f"(d[55]),
        "+f"(d[56]), "+f"(d[57]), "+f"(d[58]), "+f"(d[59]), "+f"(d[60]), "+f"(d[61]), "+f"(d[62]), "+f"(d[63]),
        "+f"(d[64]), "+f"(d[65]), "+f"(d[66]), "+f"(d[67]), "+f"(d[68]), "+f"(d[69]), "+f"(d[70]), "+f"(d[71]),
        "+f"(d[72]), "+f"(d[73]), "+f"(d[74]), "+f"(d[75]), "+f"(d[76]), "+f"(d[77]), "+f"(d[78]), "+f"(d[79]),
        "+f"(d[80]), "+f"(d[81]), "+f"(d[82]), "+f"(d[83]), "+f"(d[84]), "+f"(d[85]), "+f"(d[86]), "+f"(d[87]),
        "+f"(d[88]), "+f"(d[89]), "+f"(d[90]), "+f"(d[91]), "+f"(d[92]), "+f"(d[93]), "+f"(d[94]), "+f"(d[95])
      : "r"(da), "n"(HA), "r"(db), "n"(HB), "r"(sc));
  }
};

struct FftConst {
  uint32_t f[2][4], fi[4][4];
  uint32_t ta[2][2], tb[2][2];
};
__device__ __forceinline__ void cis(int m, float scale, float& c, float& s) {
  const float a = (float)m * (-6.283185307179586f * scale);
  c = __cosf(a);
  s = __sinf(a);
}
__device__ __forceinline__ void fft_tables(uint32_t (&v)[12], int tw) {
  const int row = tw >> 2, ch = tw & 3;
#pragma unroll
  for (int i = 0; i < 4; i++) {
    float c[2], s[2], x[2];
#pragma unroll
    for (int e = 0; e < 2; e++) {
      cis((((32 * (8 * ch + 2 * i + e) + 15) * (4 * row - 63) + 2048) & 4095) - 2048, 1.f / 4096, c[e], s[e]);
      float gc, gs;
      cis((((row & 15) * (8 * (ch & 1) + 2 * i + e) + 8) & 15) - 8, 1.f / 16, gc, gs);
      x[e] = (row >> 4) == (ch >> 1) ? gc : (ch >> 1) ? gs : -gs;
    }
    v[i] = pack2(c[0] * 0.125f, c[1] * 0.125f);
    v[4 + i] = pack2(s[0] * 0.125f, s[1] * 0.125f);
    v[8 + i] = pack2(x[0], x[1]);
  }
#pragma unroll
  for (int i = 0; i < 12; i++) asm volatile("" : "+r"(v[i]));
}
__device__ __forceinline__ void fft_tables_store(const uint32_t (&v)[12], uint32_t sb, int tw) {
  const int row = tw >> 2;
  const uint32_t x = ((tw ^ (row >> 1)) & 3) << 4, a = sb + OFF_FT + (16 * (row >> 3) + (row & 7)) * 64 + x;
  sts128(a, v[0], v[1], v[2], v[3]);
  sts128(a + 512, v[4], v[5], v[6], v[7]);
  sts128(sb + OFF_GT + row * 64 + x, v[8], v[9], v[10], v[11]);
}
__device__ __forceinline__ void fft_twiddles(uint32_t (&v)[2], int tw) {
  float a[2], s[2];
#pragma unroll
  for (int i = 0; i < 2; i++) {
    float c;
    cis((2 * (2 * (tw & 3) + i) - 15) * (4 * (tw >> 2) - 63), 1.f / 4096, c, s[i]);
    a[i] = __fdividef(-s[i], 1.f + c);
  }
  v[0] = pack2(a[0], a[1]);
  v[1] = pack2(s[0], s[1]);
  asm volatile("" : "+r"(v[0]), "+r"(v[1]));
}
__device__ __forceinline__ void fft_matrices(FftConst& k, uint32_t sb, int w, int lane) {
  const uint32_t x = (lane >> 1) & 3;
  const uint2 t0 = lds64(sb + OFF_TT + 256 * w + 8 * lane), t1 = lds64(sb + OFF_TT + 256 * w + 8 * (lane ^ 3));
  k.ta[0][0] = t0.x;
  k.tb[0][0] = t0.y;
  k.ta[1][1] = __byte_perm(t1.x, 0, 0x1032);
  k.tb[1][1] = __byte_perm(t1.y, 0, 0x1032);
#pragma unroll
  for (int j = 0; j < 2; j++) {
    k.ta[1 - j][j] = k.ta[j][j] ^ 0x80008000u;
    k.tb[1 - j][j] = k.tb[j][j] ^ 0x80008000u;
    asm volatile("" : "+r"(k.ta[0][j]), "+r"(k.tb[0][j]), "+r"(k.ta[1][j]), "+r"(k.tb[1][j]));
  }
#pragma unroll
  for (int i = 0; i < 2; i++) {
    ldsm4(k.f[i], sb + OFF_FT + (16 * w + (lane & 15)) * 64 + (((2 * i + (lane >> 4)) ^ x) << 4));
    ldsm4t(k.fi[i], sb + OFF_FT + (32 * i + lane) * 64 + ((w ^ x) << 4));
#pragma unroll
    for (int j = 0; j < 4; j++) {
      k.fi[2 + i][j] = (j & 1) ? k.fi[i][j - 1] ^ 0x80008000u : k.fi[i][j + 1];
      asm volatile("" : "+r"(k.fi[2 + i][j]));
    }
  }
}
__device__ __forceinline__ void rot(uint32_t& x, uint32_t& y, uint32_t a, uint32_t b) {
  x = bfma(a, y, x);
  y = bfma(b, x, y);
  x = bfma(a, y, x);
}
__device__ __forceinline__ void twiddle_fwd(uint32_t (&a)[4][4], float* d, const FftConst& k) {
#pragma unroll
  for (int q = 0; q < 4; q++)
#pragma unroll
    for (int j = 0; j < 2; j++) {
      const float* x = d + 8 * q + 4 * j;
      uint32_t re = pack2(x[0], x[1]), im = pack2(x[2], x[3]);
      rot(re, im, k.ta[0][j], k.tb[0][j]);
      a[q & 2][2 * j + (q & 1)] = re;
      a[(q & 2) + 1][2 * j + (q & 1)] = im;
    }
}
__device__ __forceinline__ void g_step(float* d, const uint32_t (&a)[4][4], uint32_t dre, uint32_t dim) {
  WgRS<32>::set<HI_SW64>(d, a[0], dre);
  WgRS<32>::set<HI_SW64>(d + 16, a[2], dre);
  WgRS<32>::mma<HI_SW64>(d, a[1], dim);
  WgRS<32>::mma<HI_SW64>(d + 16, a[3], dim);
  wg_commit();
}

__device__ __forceinline__ void products(uint32_t (&a)[4][4], const float* H, const float* U, int p) {
#pragma unroll
  for (int j = 0; j < 2; j++)
#pragma unroll
    for (int m = 2 * p; m < 2 * p + 2; m++) {
      float pr[2], pi[2];
#pragma unroll
      for (int x = 0; x < 2; x++)
#pragma unroll
        for (int q = 0; q <= m; q++) {
          const int ih = 16 * (q >> 1) + 2 * (q & 1) + 4 * j + x, iu = 16 * ((m - q) >> 1) + 2 * ((m - q) & 1) + 4 * j + x;
          pr[x] = q ? fmaf(H[ih], U[iu], pr[x]) : H[ih] * U[iu];
          pi[x] = q ? fmaf(H[ih], U[iu + 8], pi[x]) : H[ih] * U[iu + 8];
          pr[x] = fmaf(-H[ih + 8], U[iu + 8], pr[x]);
          pi[x] = fmaf(H[ih + 8], U[iu], pi[x]);
        }
      a[m & 2][2 * j + (m & 1)] = pack2(pr[0], pr[1]);
      a[(m & 2) + 1][2 * j + (m & 1)] = pack2(pi[0], pi[1]);
    }
}

__device__ __forceinline__ void conv_channel(const FftConst& k, uint32_t sb, int c, int wg, int w, int lane) {
  const uint32_t cb = sb + off_ch(c), bars = sb + OFF_BAR;
  const uint32_t du = desc_lo(cb, 1024), dg = desc_lo(sb + OFF_GT, 16), dz = desc_lo(cb + U_BYTES, 16);
  float U[32], H[32];
  uint32_t a[4][4], e[4][4];
  const float dv = __uint_as_float(lds32(sb + OFF_D + 4 * c));
  wg_fence();
  WgRS<64>::set<HI_SW32>(H, k.f[0], du + 256);
  WgRS<64>::mma<HI_SW32>(H, k.f[1], du + 256 + 32);
  wg_commit();
  wg_wait<0>();
  pin<32>(H);
  twiddle_fwd(a, H, k);
  if (ATT_GATE) mbar_wait(bars + 8 * (ATT_GATE == 1 ? B_ATTN : B_ATT2), 0);
  mbar_wait(bars + 8 * (B_U + (c < 3 ? c : 3)), 0);
  TSM(w == 0 && c < 3, 7 + wg);
  wg_fence();
  WgRS<64>::set<HI_SW32>(U, k.f[0], du);
  WgRS<64>::mma<HI_SW32>(U, k.f[1], du + 32);
  wg_commit();
  g_step(H, a, dg, dg + 64);
  wg_wait<1>();
  pin<32>(U);
  twiddle_fwd(e, U, k);
  wg_fence();
  g_step(U, e, dg, dg + 64);
  wg_wait<0>();
  pin<32>(U);
  pin<32>(H);
#pragma unroll
  for (int j = 0; j < 4; j++) H[4 * (j >> 1) + (j & 1)] += dv;
  float V[32];
#pragma unroll
  for (int p = 0; p < 2; p++) {
    products(a, H, U, p);
    wg_fence();
    WgRS<32>::set<HI_SW64>(V + 16 * p, a[2 * p], dg + 64);
    WgRS<32>::mma<HI_SW64>(V + 16 * p, a[2 * p + 1], dg);
    wg_commit();
  }
  const uint32_t za = cb + U_BYTES + (8 * w + (lane & 7)) * 128 + (((lane >> 3) ^ (lane & 7)) << 4);
  const uint32_t ya = cb + (lane >> 4) * 1024 + (8 * w + (lane & 7)) * 32 + ((((lane >> 3) ^ (lane >> 2)) & 1) << 4);
  wg_sync(1 + wg);
#pragma unroll
  for (int p = 0; p < 2; p++) {
    if (p == 0) wg_wait<1>();
    else wg_wait<0>();
    pin<16>(V + 16 * p);
#pragma unroll
    for (int i = 0; i < 4; i++) {
      const int j = i & 1;
      const float* x = V + 16 * p + 4 * j + (i & 2);
      e[p][i] = pack2(x[8], x[9]);
      e[2 + p][i] = pack2(x[0], x[1]);
      rot(e[p][i], e[2 + p][i], k.ta[1][j], k.tb[1][j]);
    }
    stsm4(za ^ (64 * p), e[p]);
    stsm4((za ^ (64 * p)) + 4096, e[2 + p]);
  }
  fence_async_smem();
  wg_sync(1 + wg);
  wg_fence();
  WgRS<64>::set<HI_SW128>(H, k.fi[0], dz);
#pragma unroll
  for (int ks = 1; ks < 4; ks++) WgRS<64>::mma<HI_SW128>(H, k.fi[ks], dz + 128 * ks);
  wg_commit();
  if (WO_GATE == 3 && lane == 0) mbar_arrive(bars + 8 * B_CVD);
  wg_wait<0>();
  pin<32>(H);
  if (WO_GATE == 4 && lane == 0) mbar_arrive(bars + 8 * B_CVD);
  TSIF(w == 0, 88 + c);
#pragma unroll
  for (int j = 0; j < 8; j++)
    a[j >> 2][j & 3] = j < 2 ? pack2(H[4 * j], H[4 * j + 1]) : pack2(H[4 * j] + H[4 * j - 6], H[4 * j + 1] + H[4 * j - 5]);
  stsm4(ya, a[0]);
  stsm4(ya + 2048, a[1]);
  fence_async_smem();
  __syncwarp();
}

__device__ __forceinline__ void prep_slab(uint4* res, const uint2* sw, uint32_t sb, int slab, int w, int lane) {
  const int t = lane & 3, tp = (lane & 7) >> 1, pos = 8 * tp + 2 * (((lane >> 3) + tp) & 3) + (lane & 1);
  const uint32_t base = sb + OFF_KVS + slab * KVS_BYTES + pos * 128;
  uint32_t kk[2][4][4], vv[2][4];
  mbar_wait(sb + OFF_BAR + 8 * (B_KV + slab), 0);
#pragma unroll
  for (int h = 0; h < 2; h++) {
#pragma unroll
    for (int j = 0; j < 4; j++) {
      const uint32_t a = base + 128 * j;
      ldsm4t(kk[h][j], a + (((w + 4 * h) ^ ((a >> 7) & 7)) << 4));
    }
    const uint32_t a = base + KVS_V;
    ldsm4t(vv[h], a + (((w + 4 * h) ^ ((a >> 7) & 7)) << 4));
  }
#pragma unroll
  for (int h = 0; h < 2; h++) {
    uint32_t (&k)[4][4] = kk[h];
    uint32_t (&v)[4] = vv[h];
    const uint32_t w0 = __byte_perm(sw[h].x, 0, 0x1010), w1 = __byte_perm(sw[h].x, 0, 0x3232);
    const uint32_t w2 = __byte_perm(sw[h].y, 0, 0x1010), w3 = __byte_perm(sw[h].y, 0, 0x3232);
#pragma unroll
    for (int m = 0; m < 4; m++)
      v[m] = bmul(badd(badd(badd(bmul(k[0][m], w3), bmul(k[1][m], w2)), bmul(k[2][m], w1)), bmul(k[3][m], w0)), v[m]);
    uint32_t a[4];
#pragma unroll
    for (int m = 0; m < 4; m++) a[m] = (t & 1) ? v[(m + 3) & 3] : v[m];
    res[h] = (t & 2) ? make_uint4(a[2], a[3], a[0], a[1]) : make_uint4(a[0], a[1], a[2], a[3]);
  }
}

__device__ __forceinline__ void prep_gate(const Params& p, uint32_t sb, int b, int w, int lane) {
  uint2 gw[5], x[4][5];
#pragma unroll
  for (int j = 0; j < 5; j++) gw[j] = ldg64(reinterpret_cast<const uint2*>(p.gate_w) + lane + 32 * j);
#pragma unroll
  for (int i = 0; i < 4; i++)
#pragma unroll
    for (int j = 0; j < 5; j++)
      x[i][j] = ldg64(reinterpret_cast<const uint2*>(p.q) + (16 * b + 4 * w + i) * (DIM / 4) + lane + 32 * j);
  float s[4];
#pragma unroll
  for (int i = 0; i < 4; i++) {
    s[i] = 0.f;
#pragma unroll
    for (int j = 0; j < 5; j++) {
      const uint32_t m0 = bmul(x[i][j].x, gw[j].x), m1 = bmul(x[i][j].y, gw[j].y);
      s[i] += (bf_lo(m0) + bf_hi(m0)) + (bf_lo(m1) + bf_hi(m1));
    }
  }
  const bool h = lane & 16, q = lane & 8;
  const float a = (h ? s[2] : s[0]) + __shfl_xor_sync(0xffffffffu, h ? s[0] : s[2], 16);
  const float c = (h ? s[3] : s[1]) + __shfl_xor_sync(0xffffffffu, h ? s[1] : s[3], 16);
  float z = (q ? c : a) + __shfl_xor_sync(0xffffffffu, q ? a : c, 8);
#pragma unroll
  for (int o = 4; o > 0; o >>= 1) z += __shfl_xor_sync(0xffffffffu, z, o);
  z = bf_lo(pack2(z, 0.f));
  z = bf_lo(pack2(__fdividef(1.f, 1.f + __expf(-z)), 0.f));
  if (G_TMA) {
    mbar_wait(sb + OFF_BAR + 8 * B_S3, 0);
    if ((lane & 7) == 0) asm volatile("st.shared.f32 [%0], %1;" ::"r"(sb + OFF_GATE + 64 * (b & 7) + 16 * w + (lane >> 1)), "f"(z) : "memory");
    fence_async_smem();
  } else if ((lane & 7) == 0) {
    g_gate[16 * b + 4 * w + (lane >> 3)] = z;
  }
}

__device__ __forceinline__ uint32_t bmax(uint32_t a, uint32_t b) {
  uint32_t d;
  asm("max.bf16x2 %0, %1, %2;" : "=r"(d) : "r"(a), "r"(b));
  return d;
}
__device__ __forceinline__ void softmax_two(const float (&l)[2][2], uint32_t& p0, uint32_t& p1) {
  constexpr float kScale = 0.22360679774997896f, kLog2e = 1.4426950408889634f;
  const uint32_t r0 = pack2(l[0][0], l[1][0]), r1 = pack2(l[0][1], l[1][1]);
  const uint32_t x0 = pack2(bf_lo(r0) * kScale, bf_hi(r0) * kScale), x1 = pack2(bf_lo(r1) * kScale, bf_hi(r1) * kScale);
  uint32_t m = bmax(x0, x1);
  m = bmax(m, __shfl_xor_sync(0xffffffffu, m, 1));
  m = bmax(m, __shfl_xor_sync(0xffffffffu, m, 2));
  const float m0 = bf_lo(m) * kLog2e, m1 = bf_hi(m) * kLog2e;
  p0 = pack2(ex2(bf_lo(x0) * kLog2e - m0), ex2(bf_lo(x1) * kLog2e - m0));
  p1 = pack2(ex2(bf_hi(x0) * kLog2e - m1), ex2(bf_hi(x1) * kLog2e - m1));
}

__device__ __forceinline__ void halo_read(uint32_t (&kpv)[10], uint32_t (&vpv)[10], uint32_t (&tg)[7], const uint4* hp) {
#pragma unroll
  for (int j = 0; j < 7; j++) {
    uint32_t x0, x1, x2;
    asm volatile("ld.relaxed.gpu.global.v4.u32 {%0, %1, %2, %3}, [%4];"
                 : "=r"(x0), "=r"(x1), "=r"(x2), "=r"(tg[j]) : "l"(hp + 32 * j) : "memory");
    if (j < 4) kpv[3 * j] = x0; else vpv[3 * j - 10] = x0;
    if (j < 3) kpv[3 * j + 1] = x1; else vpv[3 * j - 9] = x1;
    if (j < 3) kpv[3 * j + 2] = x2; else if (j < 6) vpv[3 * j - 8] = x2;
  }
}

template <int ROT>
__device__ __forceinline__ void pack_qkv(const float* acc, uint32_t (&qlo)[10], uint32_t (&qhi)[10], uint32_t (&klo)[10],
                                         uint32_t (&khi)[10], uint32_t (&vlo)[10], uint32_t (&vhi)[10]) {
#pragma unroll
  for (int j = 0; j < 10; j++) {
    const int x = (j + ROT) % 10, tq = x < 8 ? x : 16 + x, tk = x < 8 ? 8 + x : 18 + x, tv = x < 8 ? 16 + x : 20 + x;
    khi[j] = pack2(acc[4 * tk + 2], acc[4 * tk + 3]);
    vhi[j] = movm(pack2(acc[4 * tv + 2], acc[4 * tv + 3]));
    qlo[j] = pack2(acc[4 * tq], acc[4 * tq + 1]);
    qhi[j] = pack2(acc[4 * tq + 2], acc[4 * tq + 3]);
    klo[j] = pack2(acc[4 * tk], acc[4 * tk + 1]);
    vlo[j] = pack2(acc[4 * tv], acc[4 * tv + 1]);
    asm volatile("" : "+r"(khi[j]), "+r"(qlo[j]), "+r"(qhi[j]), "+r"(klo[j]), "+r"(vlo[j]));
  }
}

template <int ROT> __device__ __forceinline__ void halo_send(const float* acc, uint4* ho, uint32_t tag) {
#pragma unroll
  for (int j = 0; j < 7; j++) {
    uint32_t x[3];
#pragma unroll
    for (int e = 0; e < 3; e++) {
      const int i = 3 * j + e, y = (i % 10 + ROT) % 10, tk = y < 8 ? 8 + y : 18 + y, tv = y < 8 ? 16 + y : 20 + y;
      x[e] = i < 10 ? pack2(acc[4 * tk + 2], acc[4 * tk + 3]) : i < 20 ? movm(pack2(acc[4 * tv + 2], acc[4 * tv + 3])) : 0u;
    }
    asm volatile("st.relaxed.gpu.global.v4.u32 [%0], {%1, %2, %3, %4};" ::"l"(ho + 32 * j), "r"(x[0]), "r"(x[1]), "r"(x[2]), "r"(tag) : "memory");
  }
}

__device__ __forceinline__ void attention(float* acc, uint32_t sb, int b, int par, int w, int lane, uint32_t tag, uint32_t zero) {
  const int g = lane >> 2, t = lane & 3;
  uint32_t klo[10], khi[10], vlo[10], vhi[10], qlo[10], qhi[10], kpv[10], vpv[10];
  if (HALO_FIRST && w == 3 && b < NCTA - 8) {
    uint4* ho = g_halo + (b * 2 + par) * 224 + lane;
    if (tail_first(b & 7)) halo_send<8>(acc, ho, tag);
    else halo_send<0>(acc, ho, tag);
    TSIF(par == 0, 76);
    pin<120>(acc);
  }
  if (tail_first(b & 7)) pack_qkv<8>(acc, qlo, qhi, klo, khi, vlo, vhi);
  else pack_qkv<0>(acc, qlo, qhi, klo, khi, vlo, vhi);
  const uint32_t xa = sb + OFF_KVX + (par * 3) * 2560 + lane * 16;
  if (w < 3) {
    sts128(xa + w * 2560, khi[0], khi[1], khi[2], khi[3]);
    sts128(xa + w * 2560 + 512, khi[4], khi[5], khi[6], khi[7]);
    sts128(xa + w * 2560 + 1024, khi[8], khi[9], vhi[0], vhi[1]);
    sts128(xa + w * 2560 + 1536, vhi[2], vhi[3], vhi[4], vhi[5]);
    sts128(xa + w * 2560 + 2048, vhi[6], vhi[7], vhi[8], vhi[9]);
  } else if (!HALO_FIRST && b < NCTA - 8) {
    uint4* ho = g_halo + (b * 2 + par) * 224 + lane;
#pragma unroll
    for (int j = 0; j < 7; j++) {
      const uint32_t x0 = j < 4 ? khi[3 * j] : vhi[3 * j - 10], x1 = j < 3 ? khi[3 * j + 1] : vhi[3 * j - 9];
      const uint32_t x2 = j < 3 ? khi[3 * j + 2] : j < 6 ? vhi[3 * j - 8] : 0u;
      asm volatile("st.relaxed.gpu.global.v4.u32 [%0], {%1, %2, %3, %4};" ::"l"(ho + 32 * j), "r"(x0), "r"(x1), "r"(x2), "r"(tag) : "memory");
    }
  }
  TSIF(par == 0 && w == 1, 64);
  TSIF(par == 0 && w == 3 && !HALO_FIRST, 76);
#pragma unroll
  for (int j = 0; j < 10; j++) vlo[j] = movm(vlo[j]);
  const bool far0 = 2 * t > g, far1 = 2 * t + 1 > g;
  const uint32_t mfar = (far0 ? 0x0000FFFFu : 0u) | (far1 ? 0xFFFF0000u : 0u);
  float slo[4][2], shi[4][2], lg[2][2];
  uint32_t phi[4], plo[4], qml[4], qmh[4];
#pragma unroll
  for (int h = 0; h < 4; h++) {
    const int f = h == 0 ? 0 : h == 1 ? 3 : h == 2 ? 5 : 8, hf = h < 2 ? 2 : 7;
    const bool mine = (h & 1) ? t >= 2 : t < 2;
    qml[h] = mine ? qlo[hf] : 0u;
    qmh[h] = mine ? qhi[hf] : 0u;
    float a[4] = {0.f, 0.f, 0.f, 0.f}, c[4] = {0.f, 0.f, 0.f, 0.f};
    mma16816(a, qlo[f], qhi[f], qlo[f + 1], qhi[f + 1], klo[f], klo[f + 1]);
    mma16816(c, qlo[f], qhi[f], qlo[f + 1], qhi[f + 1], khi[f], khi[f + 1]);
    mma1688(a, qml[h], qmh[h], klo[hf]);
    mma1688(c, qml[h], qmh[h], khi[hf]);
    slo[h][0] = a[0];
    slo[h][1] = a[1];
    shi[h][0] = lg[h & 1][0] = far0 ? a[2] : c[2];
    shi[h][1] = lg[h & 1][1] = far1 ? a[3] : c[3];
    if (!ATT_MERGE && (h & 1)) softmax_two(lg, phi[h - 1], phi[h]);
  }
  TSIF(par == 0 && w == 1, 65);
  if (ATT_GATE == 3 && lane == 0) mbar_arrive(sb + OFF_BAR + 8 * B_ATT2 + (phi[3] & zero));
  wg_sync(1 + par);
  TSIF(par == 0 && w == 1, 66);
  const bool nohist = (w == 0) && (b < 8);
  const uint4* hp = g_halo + ((b - 8) * 2 + par) * 224 + lane;
  uint32_t tg[7];
  if (w > 0) {
    const uint4 v0 = lds128(xa + (w - 1) * 2560), v1 = lds128(xa + (w - 1) * 2560 + 512), v2 = lds128(xa + (w - 1) * 2560 + 1024);
    const uint4 v3 = lds128(xa + (w - 1) * 2560 + 1536), v4 = lds128(xa + (w - 1) * 2560 + 2048);
    kpv[0] = v0.x; kpv[1] = v0.y; kpv[2] = v0.z; kpv[3] = v0.w; kpv[4] = v1.x; kpv[5] = v1.y; kpv[6] = v1.z; kpv[7] = v1.w;
    kpv[8] = v2.x; kpv[9] = v2.y; vpv[0] = v2.z; vpv[1] = v2.w; vpv[2] = v3.x; vpv[3] = v3.y; vpv[4] = v3.z; vpv[5] = v3.w;
    vpv[6] = v4.x; vpv[7] = v4.y; vpv[8] = v4.z; vpv[9] = v4.w;
  } else if (nohist) {
#pragma unroll
    for (int j = 0; j < 10; j++) kpv[j] = vpv[j] = 0u;
  } else {
    TSIF(par == 0, 77);
    halo_read(kpv, vpv, tg, hp);
  }
  if (w == 0 && !nohist) {
    int spins = 0;
    while (true) {
      bool ok = true;
#pragma unroll
      for (int j = 0; j < 7; j++) ok = ok && tg[j] == tag;
      if (__all_sync(0xffffffffu, ok) || ++spins > SPIN_LIMIT) break;
      halo_read(kpv, vpv, tg, hp);
    }
    TSIF(par == 0, 79);
  }
#pragma unroll
  for (int h = 0; h < 4; h++) {
    const int f = h == 0 ? 0 : h == 1 ? 3 : h == 2 ? 5 : 8, hf = h < 2 ? 2 : 7;
    float a[4] = {0.f, 0.f, 0.f, 0.f};
    mma16816(a, qlo[f], qhi[f], qlo[f + 1], qhi[f + 1], kpv[f], kpv[f + 1]);
    mma1688(a, qml[h], qmh[h], kpv[hf]);
    const float ninf = __int_as_float(0xff800000);
    lg[h & 1][0] = far0 ? (nohist ? ninf : a[0]) : slo[h][0];
    lg[h & 1][1] = far1 ? (nohist ? ninf : a[1]) : slo[h][1];
    if (h & 1) {
      softmax_two(lg, plo[h - 1], plo[h]);
      if (ATT_MERGE) {
        const float lh[2][2] = {{shi[h - 1][0], shi[h - 1][1]}, {shi[h][0], shi[h][1]}};
        softmax_two(lh, phi[h - 1], phi[h]);
      }
    }
  }
  TSIF(par == 0 && w <= 1, 67 + w);
  if (ATT_GATE == 2 && lane == 0) mbar_arrive(sb + OFF_BAR + 8 * B_ATT2 + (plo[3] & zero));
  uint32_t ov[20];
#pragma unroll
  for (int hp = 0; hp < 2; hp++) {
    const int hf = hp ? 7 : 2;
    float sh[4] = {0.f, 0.f, 0.f, 0.f}, i0 = 0.f, i1 = 0.f;
#pragma unroll
    for (int e = 0; e < 2; e++) {
      const int h = 2 * hp + e, f = h == 0 ? 0 : h == 1 ? 3 : h == 2 ? 5 : 8;
      const uint32_t a0 = plo[h] & mfar, a2 = plo[h] & ~mfar, a3 = phi[h] & mfar, c1 = phi[h] & ~mfar;
      float sum[4] = {0.f, 0.f, 0.f, 0.f};
      mma1688(sum, plo[h], phi[h], 0x3F803F80u);
      const float r0 = rcp(sum[0]), r1 = rcp(sum[2]);
#pragma unroll
      for (int j = f; j < f + 2; j++) {
        float o[4] = {0.f, 0.f, 0.f, 0.f};
        mma16816(o, a0, 0u, a2, a3, vpv[j], vlo[j]);
        mma1688(o, 0u, c1, vhi[j]);
        ov[2 * j] = pack2(o[0] * r0, o[1] * r0);
        ov[2 * j + 1] = pack2(o[2] * r1, o[3] * r1);
      }
      const bool mine = e ? g >= 4 : g < 4;
      mma16816(sh, a0, 0u, a2, a3, mine ? vpv[hf] : 0u, mine ? vlo[hf] : 0u);
      mma1688(sh, 0u, c1, mine ? vhi[hf] : 0u);
      if (e == 0 || t >= 2) {
        i0 = r0;
        i1 = r1;
      }
    }
    ov[2 * hf] = pack2(sh[0] * i0, sh[1] * i0);
    ov[2 * hf + 1] = pack2(sh[2] * i1, sh[3] * i1);
  }
  if (ATT_GATE == 4 && lane == 0) mbar_arrive(sb + OFF_BAR + 8 * B_ATT2 + (ov[19] & zero));
  TS(32 + 4 * par + w);
  mbar_wait(sb + OFF_BAR + 8 * B_P1, 0);
  const uint32_t oa = sb + OFF_OA + (lane >> 4) * 2048 + (32 * w + 2 * (lane & 15) + par) * 16;
#pragma unroll
  for (int j = 0; j < 5; j++) stsm4(oa + 4096 * j, ov + 4 * j);
  TSIF(par == 0 && w == 0, 120);
  fence_async_smem();
  TSIF(par == 0 && w == 0, 121);
  __syncwarp();
  if (lane == 0) mbar_arrive(sb + OFF_BAR + 8 * B_ATTN);
  TSM(w == 0 || w == 2, 122 + par + (w == 2 ? 3 : 0));
}

struct Maps {
  CUtensorMap x, wm, wt, k, v, y, wo, qm, qt, om, ot, u;
};

__device__ __forceinline__ void load_stage(uint32_t sb, int kb, int b, const Maps& m) {
  const uint32_t st = sb + (kb & 3) * STAGE_BYTES, bar = sb + OFF_BAR + 8 * (B_FULL1 + (kb & 3));
  const int r = b >> 3, hg = b & 7, slab = kb - KV_KB;
  const bool kv = slab >= 0 && slab < 5;
  const uint32_t kbar = sb + OFF_BAR + 8 * (B_KV + slab), dst = sb + OFF_KVS + slab * KVS_BYTES;
  mbar_expect_tx(bar, STAGE_BYTES);
  if (kv) mbar_expect_tx(kbar, KVS_BYTES);
  tma_3d(st, &m.x, 64 * kb, 64 * r, 0, bar);
  if (kv && KV_MIX) tma_3d(dst, &m.k, 0, 32 * (b >> 1) - 3, 2 * slab + (b & 1), kbar);
  tma_3d(st + ST_W, &m.wm, 80 * hg + (tail_first(hg) ? 16 : 0), 64 * kb, 0, bar);
  if (kv && KV_MIX) tma_3d(dst + KVS_V, &m.v, 0, 32 * (b >> 1), 2 * slab + (b & 1), kbar);
  tma_3d(st + ST_WT, &m.wt, 80 * hg + (tail_first(hg) ? 0 : 64), 64 * kb, 0, bar);
  if (kv && !KV_MIX) tma_3d(dst, &m.k, 0, 32 * (b >> 1) - 3, 2 * slab + (b & 1), kbar);
  if (kv && !KV_MIX) tma_3d(dst + KVS_V, &m.v, 0, 32 * (b >> 1), 2 * slab + (b & 1), kbar);
}

__global__ void __launch_bounds__(NTHR, 1) fused_kernel(const __grid_constant__ Maps m, const Params p) {
  extern __shared__ __align__(1024) uint8_t smem[];
  const uint32_t sb = (uint32_t)__cvta_generic_to_shared(smem);
  const uint32_t bars = sb + OFF_BAR;
  const int tid = threadIdx.x, lane = tid & 31;
  int b = blockIdx.x;
  if (BMAP == 1) b = (((b & 63) >> 3) * 2 + (b & 1)) * 8 + (((b < 64 ? 0x6521 : 0x7430) >> (4 * ((b >> 1) & 3))) & 7);
  if (BMAP == 2) b = ((b & 63) >> 2) * 8 + (((b < 64 ? 0x6521 : 0x7430) >> (4 * (b & 3))) & 7);
  if (BMAP == 3) b = (((b & 63) >> 3) * 2 + (b & 1)) * 8 + (((b < 64 ? 0x7430 : 0x6521) >> (4 * ((b >> 1) & 3))) & 7);
  if (BMAP == 4) b = (((b >> 4) * 2 + (b & 1)) * 8) + ((b >> 1) & 7);
  if (BMAP == 5) b = 127 - b;
  const int r = b >> 3, hg = b & 7;

  if (tid == T_ISSUE) {
    TSM(true, 0);
#pragma unroll
    for (int i = 0; i < 4; i++) mbar_init(bars + 8 * (B_FULL1 + i), 1);
#pragma unroll
    for (int i = 0; i < 3; i++) mbar_init(bars + 8 * (B_KV + i), 1);
    fence_async_smem();
    if (T0_DELAY) {
      mbar_init(bars + 8 * B_F0, 1);
      fence_async_smem();
      mbar_expect_tx(bars + 8 * B_F0, ST_WT);
      tma_3d(sb, &m.x, 0, 64 * r, 0, bars + 8 * B_F0);
      tma_3d(sb + ST_W, &m.wm, 80 * hg + (tail_first(hg) ? 16 : 0), 0, 0, bars + 8 * B_F0);
      const long long t0 = clock64();
      while (clock64() - t0 < T0_DELAY) {}
      mbar_expect_tx(bars + 8 * B_FULL1, STAGE_BYTES - ST_WT);
      tma_3d(sb + ST_WT, &m.wt, 80 * hg + (tail_first(hg) ? 0 : 64), 0, 0, bars + 8 * B_FULL1);
    }
#pragma unroll 1
    for (int kb = T0_DELAY ? 1 : 0; kb <= PRE2; kb++) load_stage(sb, kb, b, m);
  } else if (tid >= T_PF && tid < T_PF + 12) {
    tm_prefetch(&m.x + (tid - T_PF));
  } else if (tid == T_INIT) {
#pragma unroll
    for (int i = 0; i < 4; i++) mbar_init(bars + 8 * (B_EMPTY1 + i), 8);
#pragma unroll
    for (int i = 0; i < 8; i++) mbar_init(bars + 8 * (B_FULL2 + i), 1);
#pragma unroll
    for (int i = 0; i < 4; i++) mbar_init(bars + 8 * (B_EMPTY2 + i), 8);
#pragma unroll
    for (int i = 0; i < 4; i++) mbar_init(bars + 8 * (B_U + i), 1);
    mbar_init(bars + 8 * B_HA, 4);
    mbar_init(bars + 8 * B_GATE, 4);
    mbar_init(bars + 8 * B_HB, 1);
    mbar_init(bars + 8 * B_KVD, 4);
    mbar_init(bars + 8 * B_QF, 1);
    mbar_init(bars + 8 * B_ATTN, 8);
    mbar_init(bars + 8 * B_ATT2, 8);
    mbar_init(bars + 8 * B_P1, 8);
    mbar_init(bars + 8 * B_C34, 1);
    mbar_init(bars + 8 * B_YRB, 1);
#pragma unroll
    for (int i = 0; i < 5; i++) mbar_init(bars + 8 * (B_YST + i), 4);
#pragma unroll
    for (int i = 0; i < 3; i++) mbar_init(bars + 8 * (B_US + i), U_TMA ? 4 : i == 2 ? 20 : 1);
    mbar_init(bars + 8 * B_YSIG, 1);
    mbar_init(bars + 8 * B_YFULL, 1);
    mbar_init(bars + 8 * B_EPOCH, 1);
    mbar_init(bars + 8 * B_PREP, 4);
    mbar_init(bars + 8 * B_USIG, 1);
    mbar_init(bars + 8 * B_WST, 1);
#pragma unroll
    for (int i = 3; i < 5; i++) mbar_init(bars + 8 * (B_KV + i), 1);
    mbar_init(bars + 8 * B_E3, 8);
    mbar_init(bars + 8 * B_LAST, 1);
    mbar_init(bars + 8 * B_OSIG, 1);
    mbar_init(bars + 8 * B_WOP, 1);
    fence_async_smem();
  }
  const int warp = __shfl_sync(0xffffffffu, tid >> 5, 0), wg = warp >> 2, w = warp & 3;
  __syncthreads();

  if (wg == 3) {
    asm volatile("setmaxnreg.dec.sync.aligned.u32 56;");
    if (w == 0) {
      if (lane == 0) {
#pragma unroll 1
        for (int kb = 1 + PRE2; kb < 10; kb++) {
          if (kb >= 4) mbar_wait(bars + 8 * (kb == 7 ? B_E3 : B_EMPTY1 + (kb & 3)), (kb >> 3) & 1);
          TSIF(kb >= 4, 44 + kb);
          load_stage(sb, kb, b, m);
          TSIF(kb == 3, 60);
          if (kb == TRIG_KB) mbar_arrive(bars + 8 * B_LAST);
        }
        mbar_wait(bars + 8 * B_WOP, 0);
        mbar_wait(bars + 8 * WL_TRIG, 0);
        mbar_wait(bars + 8 * B_EPOCH, 0);
        flag_wait(g_cnt + C_W + 32 * hg, (lds32(sb + OFF_EPOCH) + 1) * 16);
        TS(30);
#pragma unroll 1
        for (int j = 0; j < 8; j++) {
          if (j >= 6) mbar_wait(bars + 8 * (B_EMPTY2 + j - 6), 0);
          if (j == 4) mbar_wait(bars + 8 * B_ATTN, 0);
          TSIF(j >= 6, 100 + j);
          if (RF_GATE && j == 6) mbar_wait(bars + 8 * B_YSIG, 0);
          mbar_expect_tx(bars + 8 * (B_FULL2 + j), j == 0 ? WO_BYTES : j == 5 ? O_BYTES + WO_BYTES + 512 : O_BYTES + WO_BYTES);
          bulk_load(sb + off_w(j), g_WO + (hg * 8 + step_src(hg, j)) * 800, WO_BYTES, bars + 8 * (B_FULL2 + j));
        }
        mbar_wait(bars + 8 * (B_EMPTY2 + Q_SLOT), 0);
        mbar_expect_tx(bars + 8 * B_QF, O_BYTES);
        tma_2d(sb + OFF_QS, &m.qm, 80 * hg, 128 * r, bars + 8 * B_QF);
        if (!QBOX) tma_2d(sb + OFF_QT, &m.qt, 80 * hg + 64, 128 * r, bars + 8 * B_QF);
      }
    } else if (w == 1) {
      unsigned epoch = 0;
      if (lane == 0) {
        epoch = atomicAdd(g_cnt + C_LAUNCH, 1u) / NCTA;
        asm volatile("st.shared.u32 [%0], %1;" ::"r"(sb + OFF_EPOCH), "r"(epoch) : "memory");
        mbar_arrive(bars + 8 * B_EPOCH);
        mbar_wait(bars + 8 * B_KVD, 0);
        mbar_expect_tx(bars + 8 * B_HB, 5 * 4096);
#pragma unroll 1
        for (int c = 0; c < 5; c++) {
          if (c == 3) mbar_wait(bars + 8 * B_S3, 0);
          bulk_load(sb + off_ch(c) + U_BYTES, p.ssm_k + (5 * b + c) * SEQ, 4096, bars + 8 * B_HB);
        }
#pragma unroll
        for (int c = 0; c < 4; c++) mbar_expect_tx(bars + 8 * (B_U + c), c < 3 ? U_BYTES : 2 * U_BYTES);
        const uint4* usrc = g_U + 5 * b * U_PITCH;
        mbar_wait(bars + 8 * B_USIG, 0);
        flag_wait(g_cnt + C_PREP + 32 * (b & 15), (epoch + 1) * NCTA);
        TS(23);
#pragma unroll
        for (int c = 0; c < 5; c++) {
          if (c == 3 && U_TRIM) mbar_wait(bars + 8 * (B_U + 2), 0);
          bulk_load(sb + off_ch(c), usrc + c * U_PITCH, U_BYTES, bars + 8 * (B_U + (c < 3 ? c : 3)));
          TSIF(c == 0 || c == 4, 116 + (c >> 2));
        }
      }
      epoch = __shfl_sync(0xffffffffu, epoch, 0);
      if (lane < 8) {
        const int src = (b & ~7) | step_src(hg, lane);
        mbar_wait(bars + 8 * OP_TRIG, 0);
        TS(20);
        bool seen = false;
#pragma unroll 1
        for (int spins = 0; spins < SPIN_LIMIT; spins++) {
          const bool now = !seen && (int)(flag_read(g_cnt + C_O + 32 * src) - (epoch + 1)) >= 0;
          if (now && lane >= 1 && lane < 4) bulk_load(sb + off_o(lane), g_O + src * 1280, O_BYTES, bars + 8 * (B_FULL2 + lane));
          seen = seen || now;
          if (__all_sync(0xff, seen)) break;
        }
        TS(21);
        if (lane == 5) bulk_load(sb + OFF_GATE, g_gate + 128 * r, 512, bars + 8 * (B_FULL2 + 5));
#pragma unroll 1
        for (int j = 4; j < 8; j++) {
          if (lane == j) {
            mbar_wait(bars + 8 * (j < 6 ? B_C34 : B_EMPTY2 + j - 6), 0);
            if (RF_GATE && j == 6) mbar_wait(bars + 8 * B_YSIG, 0);
            bulk_load(sb + off_o(j), g_O + src * 1280, O_BYTES, bars + 8 * (B_FULL2 + j));
          }
          __syncwarp(0xff);
        }
        TS(22);
      }
    } else if (w == 2) {
      mbar_wait(bars + 8 * B_PREP, 0);
      flag_signal(g_cnt + C_PREP, 16, lane);
      TS(25);
      if (lane == 0) mbar_arrive(bars + 8 * B_USIG);
      mbar_wait(bars + 8 * B_GATE, 0);
      if (G_TMA) {
        if (lane == 0) {
          asm volatile("cp.async.bulk.global.shared::cta.bulk_group [%0], [%1], 64;\ncp.async.bulk.commit_group;\n"
                       "cp.async.bulk.wait_group.read 0;" ::"l"(g_gate + 16 * b), "r"(sb + OFF_GATE + 64 * hg) : "memory");
          bulk_load(sb + OFF_GATE + 64 * hg, g_gate + 16 * b, 64, bars + 8 * B_ORB);
        }
      } else if (((NOMB & 1) || O_RB) && lane == 0) {
        asm volatile("fence.release.gpu;" ::: "memory");
      }
      mbar_wait(bars + 8 * B_ATTN, 0);
      if (lane == 0) {
        if (O_DEFER) mbar_wait(bars + 8 * (B_U + 3), 0);
        asm volatile("cp.async.bulk.global.shared::cta.bulk_group [%0], [%1], 20480;\ncp.async.bulk.commit_group;"
                     ::"l"(g_O + b * 1280), "r"(sb + OFF_OA) : "memory");
        if (O_RB == 2) {
          asm volatile("cp.async.bulk.wait_group.read 0;" ::: "memory");
          mbar_expect_tx(bars + 8 * B_ORB, O_BYTES + 64 * G_TMA);
          bulk_load(sb + OFF_OA, g_O + b * 1280, O_BYTES, bars + 8 * B_ORB);
          mbar_wait(bars + 8 * B_ORB, 0);
          flag_bump(g_cnt + C_O + 32 * b);
        } else if (O_RB) asm volatile("cp.async.bulk.wait_group.read 0;" ::: "memory");
        else asm volatile("cp.async.bulk.wait_group 0;\nfence.proxy.async.global;" ::: "memory");
      }
      TS(74);
      if (O_RB == 2) {
      } else if (O_RB) {
        __syncwarp();
        unsigned v[5];
#pragma unroll
        for (int c = 0; c < 5; c++) v[c] = flag_read(reinterpret_cast<const unsigned*>(g_O + b * 1280 + 256 * c + 8 * lane + 7));
        const unsigned dep = __reduce_or_sync(0xffffffffu, (v[0] ^ v[1] ^ v[2] ^ v[3] ^ v[4]) & p.zero);
        if (lane == 0) flag_bump(g_cnt + C_O + 32 * b + dep);
      } else if (!(NOMB & 1)) flag_signal(g_cnt + C_O + 32 * b, 1, lane);
      else if (lane == 0) flag_bump(g_cnt + C_O + 32 * b);
      TS(26);
      if (lane == 0) mbar_arrive(bars + 8 * B_OSIG);

    } else {
      if (lane == 0) {
        uint4* dst = g_WO + (hg * 8 + (r >> 1)) * 800 + (r & 1) * 80;
        if (WPF) {
          mbar_wait(bars + 8 * WPF, 0);
          if (WPF_LIN)
            asm volatile("cp.async.bulk.prefetch.L2.global [%0], 6400;" ::"l"(p.wo + b * 3200) : "memory");
          else
            asm volatile("cp.async.bulk.prefetch.tensor.3d.L2.global [%0, {%1, %2, %3}];" ::"l"(&m.wo), "r"(0), "r"(40 * r), "r"(5 * hg) : "memory");
        }
        mbar_wait(bars + 8 * B_P1, 0);
        mbar_wait(bars + 8 * WB_TRIG, 0);
        mbar_expect_tx(bars + 8 * B_WST, WO_BYTES / 2);
        tma_3d(sb + OFF_WS, &m.wo, 0, 40 * r, 5 * hg, bars + 8 * B_WST);
        mbar_wait(bars + 8 * B_WST, 0);
        mbar_wait(bars + 8 * WO_TRIG, 0);
#pragma unroll 1
        for (int n = 0; n < 5; n++)
          asm volatile("cp.async.bulk.global.shared::cta.bulk_group [%0], [%1], 1280;" ::"l"(dst + 160 * n), "r"(sb + OFF_WS + 1280 * n) : "memory");
        if (W_RB) {
          asm volatile("cp.async.bulk.commit_group;\ncp.async.bulk.wait_group.read 0;" ::: "memory");
          mbar_expect_tx(bars + 8 * B_WST, WO_BYTES / 2);
#pragma unroll 1
          for (int n = 0; n < 5; n++) bulk_load(sb + OFF_WS + 1280 * n, dst + 160 * n, 1280, bars + 8 * B_WST);
          mbar_wait(bars + 8 * B_WST, 1);
        } else {
          asm volatile("cp.async.bulk.commit_group;\ncp.async.bulk.wait_group 0;\nfence.proxy.async.global;" ::: "memory");
          if (!(NOMB & 4)) asm volatile("fence.release.gpu;" ::: "memory");
        }
        flag_bump(g_cnt + C_W + 32 * hg);
        mbar_arrive(bars + 8 * B_WOP);
        TS(71);
        mbar_expect_tx(bars + 8 * B_C34, 3 * U_BYTES);
        mbar_expect_tx(bars + 8 * B_YRB, 2 * U_BYTES);
#pragma unroll 1
        for (int c = 0; c < 5; c++) {
          mbar_wait(bars + 8 * (B_YST + c), 0);
          asm volatile("cp.async.bulk.global.shared::cta.bulk_group [%0], [%1], 4096;\ncp.async.bulk.commit_group;\n"
                       "cp.async.bulk.wait_group.read 0;" ::"l"(g_Y + (5 * b + c) * Y_PITCH), "r"(sb + off_ch(c)) : "memory");
          bulk_load(sb + off_ch(c), g_Y + (5 * b + c) * Y_PITCH, U_BYTES, bars + 8 * (c < 3 ? B_C34 : B_YRB));
        }
        TS(75);
        mbar_wait(bars + 8 * B_C34, 0);
        mbar_wait(bars + 8 * B_YRB, 0);
        flag_bump(g_cnt + C_Y + 32 * (b >> 4));
        TS(27);
        mbar_arrive(bars + 8 * B_YSIG);
        mbar_expect_tx(bars + 8 * B_YFULL, 20480);
        flag_wait(g_cnt + C_Y + 32 * hg, (lds32(sb + OFF_EPOCH) + 1) * 16);
        TS(24);
        tma_2d(sb + OFF_YT, &m.y, 128 * r, 80 * hg, bars + 8 * B_YFULL);
        tma_2d(sb + OFF_YT + 10240, &m.y, 128 * r + 64, 80 * hg, bars + 8 * B_YFULL);
      }
    }
  } else {
    asm volatile("setmaxnreg.inc.sync.aligned.u32 152;");
    if (wg < 2) {
      float acc[120];
#pragma unroll
      for (int i = 0; i < 120; i++) acc[i] = 0.f;
      const uint32_t da = desc_lo(sb + wg * 8192, 16), db = desc_lo(sb + ST_W, 8192), dc = desc_lo(sb + ST_WT, 2048);
      if (PW1) pin<120>(acc);
      if (T0_DELAY) {
        mbar_wait(bars + 8 * B_F0, 0);
        TSIF(w == 0 && wg == 0, 84);
        wg_fence();
#pragma unroll
        for (int k = 0; k < 4; k++) WgSST<192>::mma<HI_SW128, HI_SW128>(acc, da + 2 * k, db + 128 * k, 1);
        wg_commit();
        mbar_wait(bars + 8 * B_FULL1, 0);
        wg_fence();
#pragma unroll
        for (int k = 0; k < 4; k++) WgSST<48>::mma<HI_SW128, HI_SW32>(acc + 96, da + 2 * k, dc + 32 * k, 1);
        wg_commit();
      }
      if (PW1 == 2) mbar_wait(bars + 8 * B_FULL1, 0);
#pragma unroll 1
      for (int kb = T0_DELAY ? 1 : 0; kb < 10; kb++) {
        mbar_wait(bars + 8 * (B_FULL1 + (kb & 3)), (kb >> 2) & 1);
        const uint32_t so = (kb & 3) * (STAGE_BYTES >> 4);
        wg_fence();
#pragma unroll
        for (int k = 0; k < 4; k++) {
          WgSST<192>::mma<HI_SW128, HI_SW128>(acc, da + so + 2 * k, db + so + 128 * k, 1);
          WgSST<48>::mma<HI_SW128, HI_SW32>(acc + 96, da + so + 2 * k, dc + so + 32 * k, 1);
        }
        wg_commit();
        wg_wait<1>();
        if (kb > 0 && lane == 0) mbar_arrive(bars + 8 * (kb == 4 ? B_E3 : B_EMPTY1 + ((kb - 1) & 3)));
      }
      mbar_wait(bars + 8 * B_EPOCH, 0);
      const uint32_t tag = lds32(sb + OFF_EPOCH) + 1;
      mbar_wait(bars + 8 * B_S3, 0);
      wg_wait<0>();
      pin<120>(acc);
      if (lane == 0) mbar_arrive(bars + 8 * B_P1);
      TSM(w == 0, 3 + wg);
      attention(acc, sb, b, wg, w, lane, tag, p.zero);
    } else {
      const int tw = tid & 127, chl = 64 * (b & 1) + 8 * w + (lane >> 2);
      uint4* up = g_U + chl * U_PITCH + ((4 * (b >> 1) + (lane & 3)) ^ ((b >> 2) & 1));
      uint2 sw[10];
      uint32_t dv = 0;
      if (lane < 5) dv = __ldg(reinterpret_cast<const unsigned short*>(p.ssm_D) + 5 * b + lane);
#pragma unroll
      for (int i = 0; i < 10; i++) sw[i] = ldg64(reinterpret_cast<const uint2*>(p.shift_k) + chl + 128 * (i >> 1) + 32 * (i & 1));
      uint32_t tab[12];
      uint32_t tt[2];
      fft_tables(tab, tw);
      fft_twiddles(tt, tw);
      uint4 res[10];
#pragma unroll
      for (int i = 0; i < 10; i++) res[i] = make_uint4(0, 0, 0, 0);
#pragma unroll 1
      for (int slab = 0; slab < 5; slab++) {
#pragma unroll
        for (int i = 0; i < 8; i++) res[i] = res[i + 2];
        prep_slab(res + 8, sw, sb, slab, w, lane);
        TSIF(w == 0, 99 + 4 * slab);
#pragma unroll
        for (int i = 0; i < 8; i++) sw[i] = sw[i + 2];
      }
      TSIF(w == 0, 28);
      __syncwarp();
      if (lane == 0) mbar_arrive(bars + 8 * B_KVD + ((res[8].x ^ res[9].x) & p.zero));
      mbar_wait(bars + 8 * B_KVD, 0);
      fft_tables_store(tab, sb, tw);
      mbar_wait(bars + 8 * B_LAST, 0);
#pragma unroll
      for (int i = 0; i < 10; i++) up[(128 * (i >> 1) + 32 * (i & 1)) * U_PITCH] = res[i];
      __syncwarp();
      if (lane == 0) mbar_arrive(bars + 8 * B_PREP);
      TSIF(w == 0 && !U_TMA, 5);
      mbar_wait(bars + 8 * (G_AFTER ? B_USIG : B_LAST), 0);
      prep_gate(p, sb, b, w, lane);
      __syncwarp();
      if (lane == 0) mbar_arrive(bars + 8 * B_GATE);
      TSIF(w == 0, 72);
      mbar_wait(bars + 8 * B_HB, 0);
      TSIF(w == 0, 2);
      const uint32_t ha = sb + U_BYTES + ((tw >> 3) * 16 + 8 + (tw & 7)) * 16;
      uint4 hv[5];
#pragma unroll
      for (int c = 0; c < 5; c++) hv[c] = lds128(ha + off_ch(c));
      __syncwarp();
#pragma unroll
      for (int c = 0; c < 5; c++) sts128((ha ^ 16) + off_ch(c), hv[c].x, hv[c].y, hv[c].z, hv[c].w);
      asm volatile("st.shared.v2.u32 [%0], {%1, %2};" ::"r"(sb + OFF_TT + 8 * tw), "r"(tt[0]), "r"(tt[1]) : "memory");
      if (tw < 5) asm volatile("st.shared.f32 [%0], %1;" ::"r"(sb + OFF_D + 4 * tw), "f"(bf_lo(dv) * 0.125f) : "memory");
      fence_async_smem();
      __syncwarp();
      if (lane == 0) mbar_arrive(bars + 8 * B_HA);
      TSIF(w == 0, 6);
    }

    FftConst fc;
    TSM(w == 0 && wg == 0, 104);
    mbar_wait(bars + 8 * B_HA, 0);
    fft_matrices(fc, sb, w, lane);
    TSM(w == 0 && wg == 0, 105);
    TSM(w == 0 && wg == 2, 124);
#pragma unroll 1
    for (uint32_t tasks = wg == 0 ? TASK0 : wg == 1 ? TASK1 : TASK2; tasks; tasks >>= 4) {
      const int c = (tasks & 7) - 1;
      conv_channel(fc, sb, c, wg, w, lane);
      if (lane == 0) mbar_arrive(bars + 8 * (B_YST + c));
      TSM(w == 0, 10 + c);
    }

    if (wg < 2) {
      const int g = lane >> 2;
      float acc[40];
#pragma unroll
      for (int i = 0; i < 40; i++) acc[i] = 0.f;
      const uint32_t da = desc_lo(sb + wg * 1024, 2048), db = desc_lo(sb, 2560);
      mbar_wait(bars + 8 * (O_RB == 2 ? B_ORB : B_ATTN), 0);
      if (PW2) mbar_wait(bars + 8 * B_FULL2, 0);
      mbar_wait(bars + 8 * B_CVD, 0);
      TSM(w == 0, 15 + wg);
#pragma unroll 1
      for (int j = 0; j < 8; j++) {
        mbar_wait(bars + 8 * (B_FULL2 + j), 0);
        TSM(w == 0 && wg == 0, 44 + (j < 4 ? j : j + 6));
        const uint32_t oa = da + (off_o(j) >> 4), ob = db + (off_w(j) >> 4);
        wg_fence();
#pragma unroll
        for (int k = 0; k < 5; k++) WgSST<80>::mma<HI_NONE, HI_SW32>(acc, oa + 256 * k, ob + 32 * k, 1);
        wg_commit();
        wg_wait<1>();
        if (j >= 1 && j <= Q_SLOT + 1 && lane == 0) mbar_arrive(bars + 8 * (B_EMPTY2 + j - 1));
      }
      TSIF(w == 0 && wg == 0, 113);
      const int tr = 64 * wg + 16 * w + (lane & 15);
      const uint32_t fm = sb + OFF_QS + tr * 128, fx = (lane >> 4) ^ (tr & 7), fq = sb + OFF_QS + tr * 160 + (lane >> 4) * 16;
      const uint32_t ft = sb + OFF_QT + tr * 32 + (((lane >> 4) ^ (tr >> 2)) & 1) * 16;
      const float g0 = __uint_as_float(lds32(sb + OFF_GATE + (64 * wg + 16 * w + g) * 4));
      const float g1 = __uint_as_float(lds32(sb + OFF_GATE + (64 * wg + 16 * w + 8 + g) * 4));
      const uint32_t ga = pack2(g0, g0), gb = pack2(g1, g1);
      const uint32_t na = pack2(1.f - g0, 1.f - g0), nb = pack2(1.f - g1, 1.f - g1);

      uint32_t qf[20];
      mbar_wait(bars + 8 * B_QF, 0);
      TSM(w == 0 && wg == 0, 99);
#pragma unroll
      for (int j = 0; j < 5; j++) ldsm4(qf + 4 * j, QBOX ? fq + 32 * j : j < 4 ? fm + ((fx ^ (2 * j)) << 4) : ft);
      if (FUSE_MIX) {
#pragma unroll
        for (int i = 0; i < 20; i++) {
          qf[i] = bmul((i & 1) ? gb : ga, qf[i]);
          asm volatile("" : "+r"(qf[i]));
        }
      }
      wg_wait<0>();
      pin<40>(acc);
      TSM(w == 0, 17 + wg);
      uint32_t pb[20];
#pragma unroll
      for (int j = 0; j < 10; j++) {
        pb[2 * j] = bmul(na, pack2(acc[4 * j], acc[4 * j + 1]));
        pb[2 * j + 1] = bmul(nb, pack2(acc[4 * j + 2], acc[4 * j + 3]));
        asm volatile("" : "+r"(pb[2 * j]), "+r"(pb[2 * j + 1]));
      }
      const uint32_t ya = sb + OFF_YT + wg * 10240 + ((lane >> 4) * 8 + (lane & 7)) * 128 +
                          (((2 * w + (((lane >> 3) & 1) ^ wg)) ^ (lane & 7)) << 4);
      mbar_wait(bars + 8 * B_YFULL, 0);
      TSM(w == 0 && wg == 0, 19);
#pragma unroll
      for (int j = 0; j < 5; j++) {
        uint32_t y[4];
        ldsm4t(y, ya + 2048 * j);
#pragma unroll
        for (int i = 0; i < 4; i++)
          qf[4 * j + i] = FUSE_MIX ? bfma(qf[4 * j + i], y[i], pb[4 * j + i]) : badd(bmul((i & 1) ? gb : ga, bmul(qf[4 * j + i], y[i])), pb[4 * j + i]);
      }
#pragma unroll
      for (int j = 0; j < 5; j++) stsm4(QBOX ? fq + 32 * j : j < 4 ? fm + ((fx ^ (2 * j)) << 4) : ft, qf + 4 * j);
      fence_async_smem();
      __syncwarp();
      if (lane == 0) {
        const int row = 64 * wg + 16 * w;
        asm volatile("cp.async.bulk.tensor.2d.global.shared::cta.bulk_group [%0, {%2, %3}], [%1];"
                     ::"l"(&m.om), "r"(sb + OFF_QS + row * (QBOX ? 160 : 128)), "r"(80 * hg), "r"(128 * r + row) : "memory");
        if (!QBOX) asm volatile("cp.async.bulk.tensor.2d.global.shared::cta.bulk_group [%0, {%2, %3}], [%1];"
                     ::"l"(&m.ot), "r"(sb + OFF_QT + row * 32), "r"(80 * hg + 64), "r"(128 * r + row) : "memory");
        asm volatile("cp.async.bulk.commit_group;\ncp.async.bulk.wait_group.read 0;" ::: "memory");
      }
      TSM(w == 0 || w == 3, 40 + 2 * wg + (w & 1));
      if (ENDBAR) asm volatile("bar.sync 15, 256;" ::: "memory");
    }
  }
}

typedef CUresult (*EncodeFn)(CUtensorMap*, CUtensorMapDataType, cuuint32_t, void*, const cuuint64_t*, const cuuint64_t*,
                             const cuuint32_t*, const cuuint32_t*, CUtensorMapInterleave, CUtensorMapSwizzle,
                             CUtensorMapL2promotion, CUtensorMapFloatOOBfill);

void encode(EncodeFn fn, CUtensorMap* tm, const void* base, int rank, const cuuint64_t* dims, const cuuint64_t* strides,
            const cuuint32_t* box, CUtensorMapSwizzle swz) {
  const cuuint32_t ones[3] = {1, 1, 1};
  fn(tm, CU_TENSOR_MAP_DATA_TYPE_BFLOAT16, rank, const_cast<void*>(base), dims, strides, box, ones,
     CU_TENSOR_MAP_INTERLEAVE_NONE, swz, CU_TENSOR_MAP_L2_PROMOTION_L2_128B, CU_TENSOR_MAP_FLOAT_OOB_FILL_NONE);
}

}

extern "C" void kernel_launch(void* const* d_in, const int* in_sizes, int n_in, void* d_out, int out_size) {
  (void)in_sizes; (void)n_in; (void)out_size;
  Params p;
  p.q = (const __nv_bfloat16*)d_in[0];
  p.k = (const __nv_bfloat16*)d_in[1];
  p.v = (const __nv_bfloat16*)d_in[2];
  p.shift_k = (const __nv_bfloat16*)d_in[3];
  p.ssm_k = (const __nv_bfloat16*)d_in[4];
  p.ssm_D = (const __nv_bfloat16*)d_in[5];
  p.wqkv = (const __nv_bfloat16*)d_in[7];
  p.wo = (const __nv_bfloat16*)d_in[8];
  p.gate_w = (const __nv_bfloat16*)d_in[9];
  p.out = (__nv_bfloat16*)d_out;
  p.zero = 0;

  static EncodeFn fn = nullptr;
  static void *yaddr = nullptr, *uaddr = nullptr;
  if (!fn) {
    cudaDriverEntryPointQueryResult qr;
    void* f = nullptr;
    cudaGetDriverEntryPoint("cuTensorMapEncodeTiled", &f, cudaEnableDefault, &qr);
    fn = (EncodeFn)f;
    cudaGetSymbolAddress(&yaddr, g_Y);
    cudaGetSymbolAddress(&uaddr, g_U);
    cudaFuncSetAttribute(fused_kernel, cudaFuncAttributeMaxDynamicSharedMemorySize, SMEM_BYTES);
  }
  Maps m;
  {
    const cuuint64_t dims[3] = {640, 1024, 2}, st[2] = {2560, 1280};
    const cuuint32_t box[3] = {64, 64, 2};
    encode(fn, &m.x, p.q, 3, dims, st, box, CU_TENSOR_MAP_SWIZZLE_128B);
  }
  {
    const cuuint64_t dims[3] = {640, 640, 3}, st[2] = {3840, 1280};
    const cuuint32_t box[3] = {64, 64, 3}, boxt[3] = {16, 64, 3};
    encode(fn, &m.wm, p.wqkv, 3, dims, st, box, CU_TENSOR_MAP_SWIZZLE_128B);
    encode(fn, &m.wt, p.wqkv, 3, dims, st, boxt, CU_TENSOR_MAP_SWIZZLE_32B);
  }
  {
    const cuuint64_t dims[3] = {64, 2048, 10}, st[2] = {1280, 128};
    const cuuint32_t boxk[3] = {64, 35, 1}, boxv[3] = {64, 32, 1};
    encode(fn, &m.k, p.k, 3, dims, st, boxk, CU_TENSOR_MAP_SWIZZLE_128B);
    encode(fn, &m.v, p.v, 3, dims, st, boxv, CU_TENSOR_MAP_SWIZZLE_128B);
  }
  {
    const cuuint64_t dims[3] = {16, 640, 40}, st[2] = {1280, 32};
    const cuuint32_t box[3] = {16, 40, 5};
    encode(fn, &m.wo, p.wo, 3, dims, st, box, CU_TENSOR_MAP_SWIZZLE_32B);
  }
  {
    const cuuint64_t dims[2] = {2048, 640}, st[1] = {Y_PITCH * 16};
    const cuuint32_t box[2] = {64, 80};
    encode(fn, &m.y, yaddr, 2, dims, st, box, CU_TENSOR_MAP_SWIZZLE_128B);
    const cuuint64_t stu[1] = {U_PITCH * 16};
    const cuuint32_t boxu[2] = {32, 64};
    encode(fn, &m.u, uaddr, 2, dims, stu, boxu, CU_TENSOR_MAP_SWIZZLE_NONE);
  }
  {
    const cuuint64_t dims[2] = {640, 2048}, st[1] = {1280};
    const cuuint32_t bqm[2] = {QBOX ? 80 : 64, 128}, bqt[2] = {16, 128}, bom[2] = {QBOX ? 80 : 64, 16}, bot[2] = {16, 16};
    encode(fn, &m.qm, p.q, 2, dims, st, bqm, QBOX ? CU_TENSOR_MAP_SWIZZLE_NONE : CU_TENSOR_MAP_SWIZZLE_128B);
    encode(fn, &m.qt, p.q, 2, dims, st, bqt, CU_TENSOR_MAP_SWIZZLE_32B);
    encode(fn, &m.om, p.out, 2, dims, st, bom, QBOX ? CU_TENSOR_MAP_SWIZZLE_NONE : CU_TENSOR_MAP_SWIZZLE_128B);
    encode(fn, &m.ot, p.out, 2, dims, st, bot, CU_TENSOR_MAP_SWIZZLE_32B);
  }
  fused_kernel<<<NCTA, NTHR, SMEM_BYTES>>>(m, p);
}
```

```cpp
#include <cuda.h>
#include <cuda_bf16.h>
#include <cuda_runtime.h>
#include <stdint.h>

namespace {

constexpr int SEQ = 2048, DIM = 640, NCTA = 128, NTHR = 512;

#define TRIG_KB 9
#define KV_KB 2
#define DEV_EXIT 0
#define ATT_GATE 0
#define G_AFTER 0
#define FENCE_LO 0
#define FENCE_HI 0
#define PW1 0
#define PW2 1
#define ENDBAR 0
#define PAD_KB 0
#define Y_ALIAS 1
#define NOMB 0
#define SRC_ROT 0
#define WAIT_NS 0
#define WB_TRIG B_USIG
#define G_POS 0
#define TAILF 1
#define T_ISSUE 384
#define T_PF 416
#define T_INIT 448
#define ATT_MERGE 0
#define BMAP 1
#define PRE2 1
#define KV_MIX 0
#define O_DEFER 0
#define TASK0 0x3
#define TASK1 0x52
#define TASK2 0x41
#define HALO_FIRST 1
#define PREV_EARLY 0
#define Y_RB 2
#define O_RB 2
#define O_EAGER 1
#define OP_TRIG B_ATTN
#define FUSE_MIX 1
#define Q_EARLY 1
#define U_TRIM 1
#define Q_SLOT 3
#define G_TMA 1
#define W_RB 1
#define WPF B_S3
#define WPF_LIN 1
#define QBOX 0
#define T0_SPLIT 2
#define ACQ 0
#define U_TMA 0
#define U_GATE 0
#define RF_GATE 0
#define WO_TRIG B_WST
#define WL_TRIG B_WOP
#define WO_GATE 4

constexpr uint32_t STAGE_BYTES = 47104, ST_W = 16384, ST_WT = 40960;
constexpr uint32_t O_BYTES = 20480, WO_BYTES = 12800;
constexpr uint32_t OFF_OA = 0;
constexpr uint32_t OFF_QS = Q_SLOT * O_BYTES, OFF_QT = OFF_QS + 16384;
constexpr uint32_t OFF_WC = 81920;
constexpr uint32_t OFF_WA = 94720;
constexpr uint32_t OFF_GATE = 145920;
constexpr uint32_t OFF_TT = 146432;
constexpr uint32_t OFF_KVX = 148480;
constexpr uint32_t OFF_CH3 = 163840;
constexpr uint32_t CH_BYTES = 12288, U_BYTES = 4096;
constexpr uint32_t OFF_FT = 225280, OFF_GT = 229376;
constexpr uint32_t OFF_CH0 = 188416;
constexpr uint32_t OFF_KVS = OFF_CH0, KVS_V = 4480, KVS_BYTES = 8576;
constexpr uint32_t OFF_WS = OFF_WA;
__device__ __forceinline__ uint32_t off_us(int s) { return OFF_CH0 + 4096 * ((0x65320 >> (4 * s)) & 7); }
constexpr uint32_t OFF_YT = 163840;
constexpr uint32_t OFF_BAR = 231936;
constexpr uint32_t SMEM_BYTES = OFF_BAR + 512;

enum : uint32_t {
  B_FULL1 = 0, B_EMPTY1 = 4, B_S3 = 7, B_FULL2 = 52, B_EMPTY2 = 13, B_U = 8, B_GATE = 12, B_HA = 19, B_HB = 20,
  B_ATTN = 21, B_C34 = 22, B_YRB = 23, B_YFULL = 24, B_EPOCH = 25, B_PREP = 26, B_P1 = 27, B_LAST = 28,
  B_E3 = 29, B_OSIG = 30, B_WOP = 31, B_USIG = 32, B_WST = 33, B_KV = 34, B_KVD = 39, B_QF = 17, B_ATT2 = 18, B_YST = 40,
  B_ORB = 45, B_F0 = 33 + 15, B_CVD = 33 + 14, B_US = 45, B_YSIG = 50
};
constexpr uint32_t OFF_EPOCH = OFF_BAR + 8 * 51, OFF_D = OFF_BAR + 8 * 60;
__device__ __forceinline__ uint32_t off_o(int j) { return j < 4 ? OFF_OA + j * O_BYTES : j < 6 ? OFF_CH0 + (j - 4) * O_BYTES : OFF_OA + (j - 6) * O_BYTES; }
__device__ __forceinline__ uint32_t off_w(int j) { return j < 4 ? OFF_WA + j * WO_BYTES : j == 4 ? OFF_KVX : j == 5 ? OFF_WC : OFF_WA + (j - 6) * WO_BYTES; }
__device__ __forceinline__ int step_src(int hg, int j) {
  if (SRC_ROT == 2) {
    const int pos = (0x37621540 >> (4 * hg)) & 7;
    return j == 0 ? hg : (0x65217430 >> (4 * (j <= pos ? j - 1 : j))) & 7;
  }
  return SRC_ROT ? (hg + j) & 7 : j == 0 ? hg : j <= hg ? j - 1 : j;
}
__device__ __forceinline__ bool tail_first(int hg) { return TAILF && (hg & 3) == 3; }
__device__ __forceinline__ uint32_t off_ch(int c) { return (c < 3 ? OFF_CH0 : OFF_CH3 - 3 * CH_BYTES) + c * CH_BYTES; }

#define U_PITCH 264
__device__ __align__(1024) uint4 g_U[DIM * U_PITCH];
__device__ uint4 g_O[NCTA * 1280];
#define g_Y g_U
constexpr int Y_PITCH = U_PITCH;
__device__ uint4 g_WO[64 * 800];
__device__ uint4 g_halo[NCTA * 2 * 7 * 32];
__device__ __align__(128) float g_gate[SEQ + PAD_KB * 256];
__device__ unsigned g_cnt[32 * (1 + 2 * 16 + 8 + NCTA)];
constexpr int C_LAUNCH = 0, C_PREP = 32, C_Y = 32 * 17, C_W = 32 * 33, C_O = 32 * 41;

#define TSM(cond, slot) do { } while (0)
#define TSIF(cond, slot) do { if (__LINE__ >= FENCE_LO && __LINE__ < FENCE_HI) sched_fence(); } while (0)
__device__ __forceinline__ void sched_fence() {
  asm volatile("{\n.reg .pred p;\n.reg .u32 c;\nmov.u32 c, %%clock;\nsetp.eq.u32 p, c, 0;\n@p st.shared.u32 [%0], c;\n}"
               ::"r"(1024 + OFF_EPOCH + 4) : "memory");
}
#define TS(slot) TSIF(true, slot)

struct Params {
  const __nv_bfloat16 *q, *k, *v, *shift_k, *ssm_k, *ssm_D, *wqkv, *wo, *gate_w;
  __nv_bfloat16* out;
  uint32_t zero;
};

#define POLL_NS 0
constexpr int SPIN_LIMIT = 1 << 17;

__device__ __forceinline__ void mbar_init(uint32_t bar, uint32_t count) {
  asm volatile("mbarrier.init.shared::cta.b64 [%0], %1;" ::"r"(bar), "r"(count) : "memory");
}
__device__ __forceinline__ void mbar_expect_tx(uint32_t bar, uint32_t bytes) {
  asm volatile("mbarrier.arrive.expect_tx.shared::cta.b64 _, [%0], %1;" ::"r"(bar), "r"(bytes) : "memory");
}
__device__ __forceinline__ void mbar_arrive(uint32_t bar) {
  asm volatile("mbarrier.arrive.shared::cta.b64 _, [%0];" ::"r"(bar) : "memory");
}
__device__ __forceinline__ void mbar_wait(uint32_t bar, uint32_t parity) {
  uint32_t ok;
  int spins = 0;
  do {
    if (WAIT_NS)
      asm volatile("{\n.reg .pred p;\nmbarrier.try_wait.parity.shared::cta.b64 p, [%1], %2, %3;\nselp.b32 %0, 1, 0, p;\n}"
                   : "=r"(ok) : "r"(bar), "r"(parity), "r"(WAIT_NS) : "memory");
    else
      asm volatile("{\n.reg .pred p;\nmbarrier.try_wait.parity.shared::cta.b64 p, [%1], %2;\nselp.b32 %0, 1, 0, p;\n}"
                   : "=r"(ok) : "r"(bar), "r"(parity) : "memory");
    if (++spins > SPIN_LIMIT) break;
  } while (!ok);
}
__device__ __forceinline__ unsigned flag_read(const unsigned* p) {
  unsigned v;
  asm volatile("ld.relaxed.gpu.global.u32 %0, [%1];" : "=r"(v) : "l"(p) : "memory");
  return v;
}
__device__ __forceinline__ void flag_poll(const unsigned* p, unsigned target) {
  unsigned v;
  int spins = 0;
  do {
    if (POLL_NS && spins) __nanosleep(POLL_NS);
    asm volatile("ld.relaxed.gpu.global.u32 %0, [%1];" : "=r"(v) : "l"(p) : "memory");
    if (++spins > SPIN_LIMIT) break;
  } while ((int)(v - target) < 0);
}
__device__ __forceinline__ void flag_wait(const unsigned* p, unsigned target) {
  flag_poll(p, target);
  if (ACQ) asm volatile("fence.acquire.gpu;\nfence.proxy.async.global;" ::: "memory");
}
__device__ __forceinline__ void flag_signal(unsigned* p, int n, int lane) {
  if (lane == 0) asm volatile("fence.release.gpu;" ::: "memory");
  __syncwarp();
  if (lane < n) asm volatile("red.relaxed.gpu.global.add.u32 [%0], 1;" ::"l"(p + 32 * lane) : "memory");
}
__device__ __forceinline__ void flag_bump(unsigned* p) {
  asm volatile("red.relaxed.gpu.global.add.u32 [%0], 1;" ::"l"(p) : "memory");
}
__device__ __forceinline__ void fence_async_smem() { asm volatile("fence.proxy.async.shared::cta;" ::: "memory"); }
__device__ __forceinline__ void wg_sync(int id) { asm volatile("bar.sync %0, 128;" ::"r"(id) : "memory"); }

__device__ __forceinline__ void tma_2d(uint32_t dst, const CUtensorMap* tm, int c0, int c1, uint32_t bar) {
  asm volatile("cp.async.bulk.tensor.2d.shared::cluster.global.mbarrier::complete_tx::bytes [%0], [%1, {%3, %4}], [%2];"
               ::"r"(dst), "l"(tm), "r"(bar), "r"(c0), "r"(c1) : "memory");
}
__device__ __forceinline__ void tma_3d(uint32_t dst, const CUtensorMap* tm, int c0, int c1, int c2, uint32_t bar) {
  asm volatile("cp.async.bulk.tensor.3d.shared::cluster.global.mbarrier::complete_tx::bytes [%0], [%1, {%3, %4, %5}], [%2];"
               ::"r"(dst), "l"(tm), "r"(bar), "r"(c0), "r"(c1), "r"(c2) : "memory");
}
__device__ __forceinline__ void bulk_load(uint32_t dst, const void* src, uint32_t bytes, uint32_t bar) {
  asm volatile("cp.async.bulk.shared::cluster.global.mbarrier::complete_tx::bytes [%0], [%1], %2, [%3];"
               ::"r"(dst), "l"(src), "r"(bytes), "r"(bar) : "memory");
}
__device__ __forceinline__ void tm_prefetch(const CUtensorMap* tm) {
  asm volatile("prefetch.tensormap [%0];" ::"l"(tm) : "memory");
}

__device__ __forceinline__ void wg_fence() { asm volatile("wgmma.fence.sync.aligned;" ::: "memory"); }
__device__ __forceinline__ void wg_commit() { asm volatile("wgmma.commit_group.sync.aligned;" ::: "memory"); }
template <int N> __device__ __forceinline__ void wg_wait() { asm volatile("wgmma.wait_group.sync.aligned %0;" ::"n"(N) : "memory"); }
__device__ __forceinline__ uint32_t desc_lo(uint32_t addr, uint32_t lbo) { return ((addr & 0x3FFFF) >> 4) | ((lbo >> 4) << 16); }
constexpr uint32_t desc_hi(uint32_t sbo, uint32_t swz) { return (sbo >> 4) | (swz << 30); }
constexpr uint32_t HI_SW128 = desc_hi(1024, 1), HI_SW64 = desc_hi(512, 2), HI_SW32 = desc_hi(256, 3), HI_NONE = desc_hi(128, 0);
template <int N> __device__ __forceinline__ void pin(float* d) {
#pragma unroll
  for (int i = 0; i < N; i++) asm volatile("" : "+f"(d[i])::"memory");
}

__device__ __forceinline__ uint32_t lds32(uint32_t a) {
  uint32_t v;
  asm volatile("ld.volatile.shared.u32 %0, [%1];" : "=r"(v) : "r"(a) : "memory");
  return v;
}
__device__ __forceinline__ uint4 ldg128(const void* a) {
  uint4 v;
  asm volatile("ld.global.nc.v4.u32 {%0, %1, %2, %3}, [%4];" : "=r"(v.x), "=r"(v.y), "=r"(v.z), "=r"(v.w) : "l"(a) : "memory");
  return v;
}
__device__ __forceinline__ uint2 ldg64(const void* a) {
  uint2 v;
  asm volatile("ld.global.nc.v2.u32 {%0, %1}, [%2];" : "=r"(v.x), "=r"(v.y) : "l"(a) : "memory");
  return v;
}
__device__ __forceinline__ void ldsm4(uint32_t* r, uint32_t a) {
  asm volatile("ldmatrix.sync.aligned.m8n8.x4.shared.b16 {%0, %1, %2, %3}, [%4];"
               : "=r"(r[0]), "=r"(r[1]), "=r"(r[2]), "=r"(r[3]) : "r"(a) : "memory");
}
__device__ __forceinline__ void ldsm4t(uint32_t* r, uint32_t a) {
  asm volatile("ldmatrix.sync.aligned.m8n8.x4.trans.shared.b16 {%0, %1, %2, %3}, [%4];"
               : "=r"(r[0]), "=r"(r[1]), "=r"(r[2]), "=r"(r[3]) : "r"(a) : "memory");
}
__device__ __forceinline__ uint2 lds64(uint32_t a) {
  uint2 v;
  asm volatile("ld.shared.v2.u32 {%0, %1}, [%2];" : "=r"(v.x), "=r"(v.y) : "r"(a) : "memory");
  return v;
}
__device__ __forceinline__ uint4 lds128(uint32_t a) {
  uint4 v;
  asm volatile("ld.shared.v4.u32 {%0, %1, %2, %3}, [%4];" : "=r"(v.x), "=r"(v.y), "=r"(v.z), "=r"(v.w) : "r"(a) : "memory");
  return v;
}
__device__ __forceinline__ void sts128(uint32_t a, uint32_t x, uint32_t y, uint32_t z, uint32_t w) {
  asm volatile("st.shared.v4.u32 [%0], {%1, %2, %3, %4};" ::"r"(a), "r"(x), "r"(y), "r"(z), "r"(w) : "memory");
}
__device__ __forceinline__ void stsm4(uint32_t a, const uint32_t* r) {
  asm volatile("stmatrix.sync.aligned.m8n8.x4.shared.b16 [%0], {%1, %2, %3, %4};" ::"r"(a), "r"(r[0]), "r"(r[1]), "r"(r[2]), "r"(r[3]) : "memory");
}
__device__ __forceinline__ void stsm4t(uint32_t a, const uint32_t* r) {
  asm volatile("stmatrix.sync.aligned.m8n8.x4.trans.shared.b16 [%0], {%1, %2, %3, %4};" ::"r"(a), "r"(r[0]), "r"(r[1]), "r"(r[2]), "r"(r[3]) : "memory");
}
__device__ __forceinline__ uint32_t pack2(float lo, float hi) {
  uint32_t r;
  asm("cvt.rn.bf16x2.f32 %0, %1, %2;" : "=r"(r) : "f"(hi), "f"(lo));
  return r;
}
__device__ __forceinline__ uint32_t movm(uint32_t a) {
  uint32_t d;
  asm volatile("movmatrix.sync.aligned.m8n8.trans.b16 %0, %1;" : "=r"(d) : "r"(a));
  return d;
}
__device__ __forceinline__ uint32_t bmul(uint32_t a, uint32_t b) {
  uint32_t d;
  asm("mul.rn.bf16x2 %0, %1, %2;" : "=r"(d) : "r"(a), "r"(b));
  return d;
}
__device__ __forceinline__ uint32_t badd(uint32_t a, uint32_t b) {
  uint32_t d;
  asm("add.rn.bf16x2 %0, %1, %2;" : "=r"(d) : "r"(a), "r"(b));
  return d;
}
__device__ __forceinline__ uint32_t bfma(uint32_t a, uint32_t b, uint32_t c) {
  uint32_t d;
  asm("fma.rn.bf16x2 %0, %1, %2, %3;" : "=r"(d) : "r"(a), "r"(b), "r"(c));
  return d;
}
__device__ __forceinline__ float bf_lo(uint32_t x) { return __uint_as_float(x << 16); }
__device__ __forceinline__ float bf_hi(uint32_t x) { return __uint_as_float(x & 0xFFFF0000u); }
__device__ __forceinline__ float ex2(float x) {
  float y;
  asm("ex2.approx.ftz.f32 %0, %1;" : "=f"(y) : "f"(x));
  return y;
}
__device__ __forceinline__ float rcp(float x) {
  float y;
  asm("rcp.approx.ftz.f32 %0, %1;" : "=f"(y) : "f"(x));
  return y;
}
__device__ __forceinline__ void mma16816(float* d, uint32_t a0, uint32_t a1, uint32_t a2, uint32_t a3, uint32_t b0, uint32_t b1) {
  asm volatile("mma.sync.aligned.m16n8k16.row.col.f32.bf16.bf16.f32 {%0, %1, %2, %3}, {%4, %5, %6, %7}, {%8, %9}, {%0, %1, %2, %3};"
               : "+f"(d[0]), "+f"(d[1]), "+f"(d[2]), "+f"(d[3])
               : "r"(a0), "r"(a1), "r"(a2), "r"(a3), "r"(b0), "r"(b1));
}
__device__ __forceinline__ void mma1688(float* d, uint32_t a0, uint32_t a1, uint32_t b0) {
  asm volatile("mma.sync.aligned.m16n8k8.row.col.f32.bf16.bf16.f32 {%0, %1, %2, %3}, {%4, %5}, {%6}, {%0, %1, %2, %3};"
               : "+f"(d[0]), "+f"(d[1]), "+f"(d[2]), "+f"(d[3])
               : "r"(a0), "r"(a1), "r"(b0));
}

template <int N> struct WgRS;
template <int N> struct WgSST;
template <> struct WgRS<32> {
  template <uint32_t HB>
  static __device__ __forceinline__ void mma(float* d, const uint32_t* a, uint32_t db) {
    asm volatile("{\n.reg .pred p;\n.reg .b64 db;\nsetp.ne.b32 p, %22, 0;\n"
      "mov.b64 db, {%20, %21};\n"
      "wgmma.mma_async.sync.aligned.m64n32k16.f32.bf16.bf16 {"
      "%0, %1, %2, %3, %4, %5, %6, %7, %8, %9, %10, %11, %12, %13, %14, %15"
      "}, {%16, %17, %18, %19}, db, p, 1, 1, 1;\n}\n"
      : "+f"(d[0]), "+f"(d[1]), "+f"(d[2]), "+f"(d[3]), "+f"(d[4]), "+f"(d[5]), "+f"(d[6]), "+f"(d[7]),
        "+f"(d[8]), "+f"(d[9]), "+f"(d[10]), "+f"(d[11]), "+f"(d[12]), "+f"(d[13]), "+f"(d[14]), "+f"(d[15])
      : "r"(a[0]), "r"(a[1]), "r"(a[2]), "r"(a[3]), "r"(db), "n"(HB), "n"(1));
  }
  template <uint32_t HB>
  static __device__ __forceinline__ void set(float* d, const uint32_t* a, uint32_t db) {
    asm volatile("{\n.reg .pred p;\n.reg .b64 db;\nsetp.ne.b32 p, %22, 0;\n"
      "mov.b64 db, {%20, %21};\n"
      "wgmma.mma_async.sync.aligned.m64n32k16.f32.bf16.bf16 {"
      "%0, %1, %2, %3, %4, %5, %6, %7, %8, %9, %10, %11, %12, %13, %14, %15"
      "}, {%16, %17, %18, %19}, db, p, 1, 1, 1;\n}\n"
      : "=f"(d[0]), "=f"(d[1]), "=f"(d[2]), "=f"(d[3]), "=f"(d[4]), "=f"(d[5]), "=f"(d[6]), "=f"(d[7]),
        "=f"(d[8]), "=f"(d[9]), "=f"(d[10]), "=f"(d[11]), "=f"(d[12]), "=f"(d[13]), "=f"(d[14]), "=f"(d[15])
      : "r"(a[0]), "r"(a[1]), "r"(a[2]), "r"(a[3]), "r"(db), "n"(HB), "n"(0));
  }
};
template <> struct WgRS<64> {
  template <uint32_t HB>
  static __device__ __forceinline__ void mma(float* d, const uint32_t* a, uint32_t db) {
    asm volatile("{\n.reg .pred p;\n.reg .b64 db;\nsetp.ne.b32 p, %38, 0;\n"
      "mov.b64 db, {%36, %37};\n"
      "wgmma.mma_async.sync.aligned.m64n64k16.f32.bf16.bf16 {"
      "%0, %1, %2, %3, %4, %5, %6, %7, %8, %9, %10, %11, %12, %13, %14, %15, "
      "%16, %17, %18, %19, %20, %21, %22, %23, %24, %25, %26, %27, %28, %29, %30, %31"
      "}, {%32, %33, %34, %35}, db, p, 1, 1, 1;\n}\n"
      : "+f"(d[0]), "+f"(d[1]), "+f"(d[2]), "+f"(d[3]), "+f"(d[4]), "+f"(d[5]), "+f"(d[6]), "+f"(d[7]),
        "+f"(d[8]), "+f"(d[9]), "+f"(d[10]), "+f"(d[11]), "+f"(d[12]), "+f"(d[13]), "+f"(d[14]), "+f"(d[15]),
        "+f"(d[16]), "+f"(d[17]), "+f"(d[18]), "+f"(d[19]), "+f"(d[20]), "+f"(d[21]), "+f"(d[22]), "+f"(d[23]),
        "+f"(d[24]), "+f"(d[25]), "+f"(d[26]), "+f"(d[27]), "+f"(d[28]), "+f"(d[29]), "+f"(d[30]), "+f"(d[31])
      : "r"(a[0]), "r"(a[1]), "r"(a[2]), "r"(a[3]), "r"(db), "n"(HB), "n"(1));
  }
  template <uint32_t HB>
  static __device__ __forceinline__ void set(float* d, const uint32_t* a, uint32_t db) {
    asm volatile("{\n.reg .pred p;\n.reg .b64 db;\nsetp.ne.b32 p, %38, 0;\n"
      "mov.b64 db, {%36, %37};\n"
      "wgmma.mma_async.sync.aligned.m64n64k16.f32.bf16.bf16 {"
      "%0, %1, %2, %3, %4, %5, %6, %7, %8, %9, %10, %11, %12, %13, %14, %15, "
      "%16, %17, %18, %19, %20, %21, %22, %23, %24, %25, %26, %27, %28, %29, %30, %31"
      "}, {%32, %33, %34, %35}, db, p, 1, 1, 1;\n}\n"
      : "=f"(d[0]), "=f"(d[1]), "=f"(d[2]), "=f"(d[3]), "=f"(d[4]), "=f"(d[5]), "=f"(d[6]), "=f"(d[7]),
        "=f"(d[8]), "=f"(d[9]), "=f"(d[10]), "=f"(d[11]), "=f"(d[12]), "=f"(d[13]), "=f"(d[14]), "=f"(d[15]),
        "=f"(d[16]), "=f"(d[17]), "=f"(d[18]), "=f"(d[19]), "=f"(d[20]), "=f"(d[21]), "=f"(d[22]), "=f"(d[23]),
        "=f"(d[24]), "=f"(d[25]), "=f"(d[26]), "=f"(d[27]), "=f"(d[28]), "=f"(d[29]), "=f"(d[30]), "=f"(d[31])
      : "r"(a[0]), "r"(a[1]), "r"(a[2]), "r"(a[3]), "r"(db), "n"(HB), "n"(0));
  }
};
template <> struct WgSST<48> {
  template <uint32_t HA, uint32_t HB>
  static __device__ __forceinline__ void mma(float* d, uint32_t da, uint32_t db, int sc) {
    asm volatile("{\n.reg .pred p;\n.reg .b64 da, db;\nsetp.ne.b32 p, %28, 0;\n"
      "mov.b64 da, {%24, %25};\nmov.b64 db, {%26, %27};\n"
      "wgmma.mma_async.sync.aligned.m64n48k16.f32.bf16.bf16 {"
      "%0, %1, %2, %3, %4, %5, %6, %7, %8, %9, %10, %11, %12, %13, %14, %15, "
      "%16, %17, %18, %19, %20, %21, %22, %23"
      "}, da, db, p, 1, 1, 0, 1;\n}\n"
      : "+f"(d[0]), "+f"(d[1]), "+f"(d[2]), "+f"(d[3]), "+f"(d[4]), "+f"(d[5]), "+f"(d[6]), "+f"(d[7]),
        "+f"(d[8]), "+f"(d[9]), "+f"(d[10]), "+f"(d[11]), "+f"(d[12]), "+f"(d[13]), "+f"(d[14]), "+f"(d[15]),
        "+f"(d[16]), "+f"(d[17]), "+f"(d[18]), "+f"(d[19]), "+f"(d[20]), "+f"(d[21]), "+f"(d[22]), "+f"(d[23])
      : "r"(da), "n"(HA), "r"(db), "n"(HB), "r"(sc));
  }
};
template <> struct WgSST<80> {
  template <uint32_t HA, uint32_t HB>
  static __device__ __forceinline__ void mma(float* d, uint32_t da, uint32_t db, int sc) {
    asm volatile("{\n.reg .pred p;\n.reg .b64 da, db;\nsetp.ne.b32 p, %44, 0;\n"
      "mov.b64 da, {%40, %41};\nmov.b64 db, {%42, %43};\n"
      "wgmma.mma_async.sync.aligned.m64n80k16.f32.bf16.bf16 {"
      "%0, %1, %2, %3, %4, %5, %6, %7, %8, %9, %10, %11, %12, %13, %14, %15, "
      "%16, %17, %18, %19, %20, %21, %22, %23, %24, %25, %26, %27, %28, %29, %30, %31, "
      "%32, %33, %34, %35, %36, %37, %38, %39"
      "}, da, db, p, 1, 1, 0, 1;\n}\n"
      : "+f"(d[0]), "+f"(d[1]), "+f"(d[2]), "+f"(d[3]), "+f"(d[4]), "+f"(d[5]), "+f"(d[6]), "+f"(d[7]),
        "+f"(d[8]), "+f"(d[9]), "+f"(d[10]), "+f"(d[11]), "+f"(d[12]), "+f"(d[13]), "+f"(d[14]), "+f"(d[15]),
        "+f"(d[16]), "+f"(d[17]), "+f"(d[18]), "+f"(d[19]), "+f"(d[20]), "+f"(d[21]), "+f"(d[22]), "+f"(d[23]),
        "+f"(d[24]), "+f"(d[25]), "+f"(d[26]), "+f"(d[27]), "+f"(d[28]), "+f"(d[29]), "+f"(d[30]), "+f"(d[31]),
        "+f"(d[32]), "+f"(d[33]), "+f"(d[34]), "+f"(d[35]), "+f"(d[36]), "+f"(d[37]), "+f"(d[38]), "+f"(d[39])
      : "r"(da), "n"(HA), "r"(db), "n"(HB), "r"(sc));
  }
};
template <> struct WgSST<192> {
  template <uint32_t HA, uint32_t HB>
  static __device__ __forceinline__ void mma(float* d, uint32_t da, uint32_t db, int sc) {
    asm volatile("{\n.reg .pred p;\n.reg .b64 da, db;\nsetp.ne.b32 p, %100, 0;\n"
      "mov.b64 da, {%96, %97};\nmov.b64 db, {%98, %99};\n"
      "wgmma.mma_async.sync.aligned.m64n192k16.f32.bf16.bf16 {"
      "%0, %1, %2, %3, %4, %5, %6, %7, %8, %9, %10, %11, %12, %13, %14, %15, "
      "%16, %17, %18, %19, %20, %21, %22, %23, %24, %25, %26, %27, %28, %29, %30, %31, "
      "%32, %33, %34, %35, %36, %37, %38, %39, %40, %41, %42, %43, %44, %45, %46, %47, "
      "%48, %49, %50, %51, %52, %53, %54, %55, %56, %57, %58, %59, %60, %61, %62, %63, "
      "%64, %65, %66, %67, %68, %69, %70, %71, %72, %73, %74, %75, %76, %77, %78, %79, "
      "%80, %81, %82, %83, %84, %85, %86, %87, %88, %89, %90, %91, %92, %93, %94, %95"
      "}, da, db, p, 1, 1, 0, 1;\n}\n"
      : "+f"(d[0]), "+f"(d[1]), "+f"(d[2]), "+f"(d[3]), "+f"(d[4]), "+f"(d[5]), "+f"(d[6]), "+f"(d[7]),
        "+f"(d[8]), "+f"(d[9]), "+f"(d[10]), "+f"(d[11]), "+f"(d[12]), "+f"(d[13]), "+f"(d[14]), "+f"(d[15]),
        "+f"(d[16]), "+f"(d[17]), "+f"(d[18]), "+f"(d[19]), "+f"(d[20]), "+f"(d[21]), "+f"(d[22]), "+f"(d[23]),
        "+f"(d[24]), "+f"(d[25]), "+f"(d[26]), "+f"(d[27]), "+f"(d[28]), "+f"(d[29]), "+f"(d[30]), "+f"(d[31]),
        "+f"(d[32]), "+f"(d[33]), "+f"(d[34]), "+f"(d[35]), "+f"(d[36]), "+f"(d[37]), "+f"(d[38]), "+f"(d[39]),
        "+f"(d[40]), "+f"(d[41]), "+f"(d[42]), "+f"(d[43]), "+f"(d[44]), "+f"(d[45]), "+f"(d[46]), "+f"(d[47]),
        "+f"(d[48]), "+f"(d[49]), "+f"(d[50]), "+f"(d[51]), "+f"(d[52]), "+f"(d[53]), "+f"(d[54]), "+f"(d[55]),
        "+f"(d[56]), "+f"(d[57]), "+f"(d[58]), "+f"(d[59]), "+f"(d[60]), "+f"(d[61]), "+f"(d[62]), "+f"(d[63]),
        "+f"(d[64]), "+f"(d[65]), "+f"(d[66]), "+f"(d[67]), "+f"(d[68]), "+f"(d[69]), "+f"(d[70]), "+f"(d[71]),
        "+f"(d[72]), "+f"(d[73]), "+f"(d[74]), "+f"(d[75]), "+f"(d[76]), "+f"(d[77]), "+f"(d[78]), "+f"(d[79]),
        "+f"(d[80]), "+f"(d[81]), "+f"(d[82]), "+f"(d[83]), "+f"(d[84]), "+f"(d[85]), "+f"(d[86]), "+f"(d[87]),
        "+f"(d[88]), "+f"(d[89]), "+f"(d[90]), "+f"(d[91]), "+f"(d[92]), "+f"(d[93]), "+f"(d[94]), "+f"(d[95])
      : "r"(da), "n"(HA), "r"(db), "n"(HB), "r"(sc));
  }
};

struct FftConst {
  uint32_t f[2][4], fi[4][4];
  uint32_t ta[2][2], tb[2][2];
};
__device__ __forceinline__ void cis(int m, float scale, float& c, float& s) {
  const float a = (float)m * (-6.283185307179586f * scale);
  c = __cosf(a);
  s = __sinf(a);
}
__device__ __forceinline__ void fft_tables(uint32_t (&v)[12], int tw) {
  const int row = tw >> 2, ch = tw & 3;
#pragma unroll
  for (int i = 0; i < 4; i++) {
    float c[2], s[2], x[2];
#pragma unroll
    for (int e = 0; e < 2; e++) {
      cis((((32 * (8 * ch + 2 * i + e) + 15) * (4 * row - 63) + 2048) & 4095) - 2048, 1.f / 4096, c[e], s[e]);
      float gc, gs;
      cis((((row & 15) * (8 * (ch & 1) + 2 * i + e) + 8) & 15) - 8, 1.f / 16, gc, gs);
      x[e] = (row >> 4) == (ch >> 1) ? gc : (ch >> 1) ? gs : -gs;
    }
    v[i] = pack2(c[0] * 0.125f, c[1] * 0.125f);
    v[4 + i] = pack2(s[0] * 0.125f, s[1] * 0.125f);
    v[8 + i] = pack2(x[0], x[1]);
  }
#pragma unroll
  for (int i = 0; i < 12; i++) asm volatile("" : "+r"(v[i]));
}
__device__ __forceinline__ void fft_tables_store(const uint32_t (&v)[12], uint32_t sb, int tw) {
  const int row = tw >> 2;
  const uint32_t x = ((tw ^ (row >> 1)) & 3) << 4, a = sb + OFF_FT + (16 * (row >> 3) + (row & 7)) * 64 + x;
  sts128(a, v[0], v[1], v[2], v[3]);
  sts128(a + 512, v[4], v[5], v[6], v[7]);
  sts128(sb + OFF_GT + row * 64 + x, v[8], v[9], v[10], v[11]);
}
__device__ __forceinline__ void fft_twiddles(uint32_t (&v)[2], int tw) {
  float a[2], s[2];
#pragma unroll
  for (int i = 0; i < 2; i++) {
    float c;
    cis((2 * (2 * (tw & 3) + i) - 15) * (4 * (tw >> 2) - 63), 1.f / 4096, c, s[i]);
    a[i] = __fdividef(-s[i], 1.f + c);
  }
  v[0] = pack2(a[0], a[1]);
  v[1] = pack2(s[0], s[1]);
  asm volatile("" : "+r"(v[0]), "+r"(v[1]));
}
__device__ __forceinline__ void fft_matrices(FftConst& k, uint32_t sb, int w, int lane) {
  const uint32_t x = (lane >> 1) & 3;
  const uint2 t0 = lds64(sb + OFF_TT + 256 * w + 8 * lane), t1 = lds64(sb + OFF_TT + 256 * w + 8 * (lane ^ 3));
  k.ta[0][0] = t0.x;
  k.tb[0][0] = t0.y;
  k.ta[1][1] = __byte_perm(t1.x, 0, 0x1032);
  k.tb[1][1] = __byte_perm(t1.y, 0, 0x1032);
#pragma unroll
  for (int j = 0; j < 2; j++) {
    k.ta[1 - j][j] = k.ta[j][j] ^ 0x80008000u;
    k.tb[1 - j][j] = k.tb[j][j] ^ 0x80008000u;
    asm volatile("" : "+r"(k.ta[0][j]), "+r"(k.tb[0][j]), "+r"(k.ta[1][j]), "+r"(k.tb[1][j]));
  }
#pragma unroll
  for (int i = 0; i < 2; i++) {
    ldsm4(k.f[i], sb + OFF_FT + (16 * w + (lane & 15)) * 64 + (((2 * i + (lane >> 4)) ^ x) << 4));
    ldsm4t(k.fi[i], sb + OFF_FT + (32 * i + lane) * 64 + ((w ^ x) << 4));
#pragma unroll
    for (int j = 0; j < 4; j++) {
      k.fi[2 + i][j] = (j & 1) ? k.fi[i][j - 1] ^ 0x80008000u : k.fi[i][j + 1];
      asm volatile("" : "+r"(k.fi[2 + i][j]));
    }
  }
}
__device__ __forceinline__ void rot(uint32_t& x, uint32_t& y, uint32_t a, uint32_t b) {
  x = bfma(a, y, x);
  y = bfma(b, x, y);
  x = bfma(a, y, x);
}
__device__ __forceinline__ void twiddle_fwd(uint32_t (&a)[4][4], float* d, const FftConst& k) {
#pragma unroll
  for (int q = 0; q < 4; q++)
#pragma unroll
    for (int j = 0; j < 2; j++) {
      const float* x = d + 8 * q + 4 * j;
      uint32_t re = pack2(x[0], x[1]), im = pack2(x[2], x[3]);
      rot(re, im, k.ta[0][j], k.tb[0][j]);
      a[q & 2][2 * j + (q & 1)] = re;
      a[(q & 2) + 1][2 * j + (q & 1)] = im;
    }
}
__device__ __forceinline__ void g_step(float* d, const uint32_t (&a)[4][4], uint32_t dre, uint32_t dim) {
  WgRS<32>::set<HI_SW64>(d, a[0], dre);
  WgRS<32>::set<HI_SW64>(d + 16, a[2], dre);
  WgRS<32>::mma<HI_SW64>(d, a[1], dim);
  WgRS<32>::mma<HI_SW64>(d + 16, a[3], dim);
  wg_commit();
}

__device__ __forceinline__ void products(uint32_t (&a)[4][4], const float* H, const float* U, int p) {
#pragma unroll
  for (int j = 0; j < 2; j++)
#pragma unroll
    for (int m = 2 * p; m < 2 * p + 2; m++) {
      float pr[2], pi[2];
#pragma unroll
      for (int x = 0; x < 2; x++)
#pragma unroll
        for (int q = 0; q <= m; q++) {
          const int ih = 16 * (q >> 1) + 2 * (q & 1) + 4 * j + x, iu = 16 * ((m - q) >> 1) + 2 * ((m - q) & 1) + 4 * j + x;
          pr[x] = q ? fmaf(H[ih], U[iu], pr[x]) : H[ih] * U[iu];
          pi[x] = q ? fmaf(H[ih], U[iu + 8], pi[x]) : H[ih] * U[iu + 8];
          pr[x] = fmaf(-H[ih + 8], U[iu + 8], pr[x]);
          pi[x] = fmaf(H[ih + 8], U[iu], pi[x]);
        }
      a[m & 2][2 * j + (m & 1)] = pack2(pr[0], pr[1]);
      a[(m & 2) + 1][2 * j + (m & 1)] = pack2(pi[0], pi[1]);
    }
}

__device__ __forceinline__ void conv_channel(const FftConst& k, uint32_t sb, int c, int wg, int w, int lane) {
  const uint32_t cb = sb + off_ch(c), bars = sb + OFF_BAR;
  const uint32_t du = desc_lo(cb, 1024), dg = desc_lo(sb + OFF_GT, 16), dz = desc_lo(cb + U_BYTES, 16);
  float U[32], H[32];
  uint32_t a[4][4], e[4][4];
  const float dv = __uint_as_float(lds32(sb + OFF_D + 4 * c));
  wg_fence();
  WgRS<64>::set<HI_SW32>(H, k.f[0], du + 256);
  WgRS<64>::mma<HI_SW32>(H, k.f[1], du + 256 + 32);
  wg_commit();
  wg_wait<0>();
  pin<32>(H);
  twiddle_fwd(a, H, k);
  if (ATT_GATE) mbar_wait(bars + 8 * (ATT_GATE == 1 ? B_ATTN : B_ATT2), 0);
  mbar_wait(bars + 8 * (B_U + (c < 3 ? c : 3)), 0);
  TSM(w == 0 && c < 3, 7 + wg);
  wg_fence();
  WgRS<64>::set<HI_SW32>(U, k.f[0], du);
  WgRS<64>::mma<HI_SW32>(U, k.f[1], du + 32);
  wg_commit();
  g_step(H, a, dg, dg + 64);
  wg_wait<1>();
  pin<32>(U);
  twiddle_fwd(e, U, k);
  wg_fence();
  g_step(U, e, dg, dg + 64);
  wg_wait<0>();
  pin<32>(U);
  pin<32>(H);
#pragma unroll
  for (int j = 0; j < 4; j++) H[4 * (j >> 1) + (j & 1)] += dv;
  float V[32];
#pragma unroll
  for (int p = 0; p < 2; p++) {
    products(a, H, U, p);
    wg_fence();
    WgRS<32>::set<HI_SW64>(V + 16 * p, a[2 * p], dg + 64);
    WgRS<32>::mma<HI_SW64>(V + 16 * p, a[2 * p + 1], dg);
    wg_commit();
  }
  const uint32_t za = cb + U_BYTES + (8 * w + (lane & 7)) * 128 + (((lane >> 3) ^ (lane & 7)) << 4);
  const uint32_t ya = cb + (lane >> 4) * 1024 + (8 * w + (lane & 7)) * 32 + ((((lane >> 3) ^ (lane >> 2)) & 1) << 4);
  wg_sync(1 + wg);
#pragma unroll
  for (int p = 0; p < 2; p++) {
    if (p == 0) wg_wait<1>();
    else wg_wait<0>();
    pin<16>(V + 16 * p);
#pragma unroll
    for (int i = 0; i < 4; i++) {
      const int j = i & 1;
      const float* x = V + 16 * p + 4 * j + (i & 2);
      e[p][i] = pack2(x[8], x[9]);
      e[2 + p][i] = pack2(x[0], x[1]);
      rot(e[p][i], e[2 + p][i], k.ta[1][j], k.tb[1][j]);
    }
    stsm4(za ^ (64 * p), e[p]);
    stsm4((za ^ (64 * p)) + 4096, e[2 + p]);
  }
  fence_async_smem();
  wg_sync(1 + wg);
  wg_fence();
  WgRS<64>::set<HI_SW128>(H, k.fi[0], dz);
#pragma unroll
  for (int ks = 1; ks < 4; ks++) WgRS<64>::mma<HI_SW128>(H, k.fi[ks], dz + 128 * ks);
  wg_commit();
  if (WO_GATE == 3 && lane == 0) mbar_arrive(bars + 8 * B_CVD);
  wg_wait<0>();
  pin<32>(H);
  if (WO_GATE == 4 && lane == 0) mbar_arrive(bars + 8 * B_CVD);
  TSIF(w == 0, 88 + c);
#pragma unroll
  for (int j = 0; j < 8; j++)
    a[j >> 2][j & 3] = j < 2 ? pack2(H[4 * j], H[4 * j + 1]) : pack2(H[4 * j] + H[4 * j - 6], H[4 * j + 1] + H[4 * j - 5]);
  stsm4(ya, a[0]);
  stsm4(ya + 2048, a[1]);
  fence_async_smem();
  __syncwarp();
}

__device__ __forceinline__ void prep_slab(uint4* res, const uint2* sw, uint32_t sb, int slab, int w, int lane) {
  const int t = lane & 3, tp = (lane & 7) >> 1, pos = 8 * tp + 2 * (((lane >> 3) + tp) & 3) + (lane & 1);
  const uint32_t base = sb + OFF_KVS + slab * KVS_BYTES + pos * 128;
  uint32_t kk[2][4][4], vv[2][4];
  mbar_wait(sb + OFF_BAR + 8 * (B_KV + slab), 0);
#pragma unroll
  for (int h = 0; h < 2; h++) {
#pragma unroll
    for (int j = 0; j < 4; j++) {
      const uint32_t a = base + 128 * j;
      ldsm4t(kk[h][j], a + (((w + 4 * h) ^ ((a >> 7) & 7)) << 4));
    }
    const uint32_t a = base + KVS_V;
    ldsm4t(vv[h], a + (((w + 4 * h) ^ ((a >> 7) & 7)) << 4));
  }
#pragma unroll
  for (int h = 0; h < 2; h++) {
    uint32_t (&k)[4][4] = kk[h];
    uint32_t (&v)[4] = vv[h];
    const uint32_t w0 = __byte_perm(sw[h].x, 0, 0x1010), w1 = __byte_perm(sw[h].x, 0, 0x3232);
    const uint32_t w2 = __byte_perm(sw[h].y, 0, 0x1010), w3 = __byte_perm(sw[h].y, 0, 0x3232);
#pragma unroll
    for (int m = 0; m < 4; m++)
      v[m] = bmul(badd(badd(badd(bmul(k[0][m], w3), bmul(k[1][m], w2)), bmul(k[2][m], w1)), bmul(k[3][m], w0)), v[m]);
    uint32_t a[4];
#pragma unroll
    for (int m = 0; m < 4; m++) a[m] = (t & 1) ? v[(m + 3) & 3] : v[m];
    res[h] = (t & 2) ? make_uint4(a[2], a[3], a[0], a[1]) : make_uint4(a[0], a[1], a[2], a[3]);
  }
}

__device__ __forceinline__ void prep_gate(const Params& p, uint32_t sb, int b, int w, int lane) {
  uint2 gw[5], x[4][5];
#pragma unroll
  for (int j = 0; j < 5; j++) gw[j] = ldg64(reinterpret_cast<const uint2*>(p.gate_w) + lane + 32 * j);
#pragma unroll
  for (int i = 0; i < 4; i++)
#pragma unroll
    for (int j = 0; j < 5; j++)
      x[i][j] = ldg64(reinterpret_cast<const uint2*>(p.q) + (16 * b + 4 * w + i) * (DIM / 4) + lane + 32 * j);
  float s[4];
#pragma unroll
  for (int i = 0; i < 4; i++) {
    s[i] = 0.f;
#pragma unroll
    for (int j = 0; j < 5; j++) {
      const uint32_t m0 = bmul(x[i][j].x, gw[j].x), m1 = bmul(x[i][j].y, gw[j].y);
      s[i] += (bf_lo(m0) + bf_hi(m0)) + (bf_lo(m1) + bf_hi(m1));
    }
  }
  const bool h = lane & 16, q = lane & 8;
  const float a = (h ? s[2] : s[0]) + __shfl_xor_sync(0xffffffffu, h ? s[0] : s[2], 16);
  const float c = (h ? s[3] : s[1]) + __shfl_xor_sync(0xffffffffu, h ? s[1] : s[3], 16);
  float z = (q ? c : a) + __shfl_xor_sync(0xffffffffu, q ? a : c, 8);
#pragma unroll
  for (int o = 4; o > 0; o >>= 1) z += __shfl_xor_sync(0xffffffffu, z, o);
  z = bf_lo(pack2(z, 0.f));
  z = bf_lo(pack2(__fdividef(1.f, 1.f + __expf(-z)), 0.f));
  if (G_TMA) {
    mbar_wait(sb + OFF_BAR + 8 * B_S3, 0);
    if ((lane & 7) == 0) asm volatile("st.shared.f32 [%0], %1;" ::"r"(sb + OFF_GATE + 64 * (b & 7) + 16 * w + (lane >> 1)), "f"(z) : "memory");
    fence_async_smem();
  } else if ((lane & 7) == 0) {
    g_gate[16 * b + 4 * w + (lane >> 3)] = z;
  }
}

__device__ __forceinline__ uint32_t bmax(uint32_t a, uint32_t b) {
  uint32_t d;
  asm("max.bf16x2 %0, %1, %2;" : "=r"(d) : "r"(a), "r"(b));
  return d;
}
__device__ __forceinline__ void softmax_two(const float (&l)[2][2], uint32_t& p0, uint32_t& p1) {
  constexpr float kScale = 0.22360679774997896f, kLog2e = 1.4426950408889634f;
  const uint32_t r0 = pack2(l[0][0], l[1][0]), r1 = pack2(l[0][1], l[1][1]);
  const uint32_t x0 = pack2(bf_lo(r0) * kScale, bf_hi(r0) * kScale), x1 = pack2(bf_lo(r1) * kScale, bf_hi(r1) * kScale);
  uint32_t m = bmax(x0, x1);
  m = bmax(m, __shfl_xor_sync(0xffffffffu, m, 1));
  m = bmax(m, __shfl_xor_sync(0xffffffffu, m, 2));
  const float m0 = bf_lo(m) * kLog2e, m1 = bf_hi(m) * kLog2e;
  p0 = pack2(ex2(bf_lo(x0) * kLog2e - m0), ex2(bf_lo(x1) * kLog2e - m0));
  p1 = pack2(ex2(bf_hi(x0) * kLog2e - m1), ex2(bf_hi(x1) * kLog2e - m1));
}

__device__ __forceinline__ void halo_read(uint32_t (&kpv)[10], uint32_t (&vpv)[10], uint32_t (&tg)[7], const uint4* hp) {
#pragma unroll
  for (int j = 0; j < 7; j++) {
    uint32_t x0, x1, x2;
    asm volatile("ld.relaxed.gpu.global.v4.u32 {%0, %1, %2, %3}, [%4];"
                 : "=r"(x0), "=r"(x1), "=r"(x2), "=r"(tg[j]) : "l"(hp + 32 * j) : "memory");
    if (j < 4) kpv[3 * j] = x0; else vpv[3 * j - 10] = x0;
    if (j < 3) kpv[3 * j + 1] = x1; else vpv[3 * j - 9] = x1;
    if (j < 3) kpv[3 * j + 2] = x2; else if (j < 6) vpv[3 * j - 8] = x2;
  }
}

template <int ROT>
__device__ __forceinline__ void pack_qkv(const float* acc, uint32_t (&qlo)[10], uint32_t (&qhi)[10], uint32_t (&klo)[10],
                                         uint32_t (&khi)[10], uint32_t (&vlo)[10], uint32_t (&vhi)[10]) {
#pragma unroll
  for (int j = 0; j < 10; j++) {
    const int x = (j + ROT) % 10, tq = x < 8 ? x : 16 + x, tk = x < 8 ? 8 + x : 18 + x, tv = x < 8 ? 16 + x : 20 + x;
    khi[j] = pack2(acc[4 * tk + 2], acc[4 * tk + 3]);
    vhi[j] = movm(pack2(acc[4 * tv + 2], acc[4 * tv + 3]));
    qlo[j] = pack2(acc[4 * tq], acc[4 * tq + 1]);
    qhi[j] = pack2(acc[4 * tq + 2], acc[4 * tq + 3]);
    klo[j] = pack2(acc[4 * tk], acc[4 * tk + 1]);
    vlo[j] = pack2(acc[4 * tv], acc[4 * tv + 1]);
    asm volatile("" : "+r"(khi[j]), "+r"(qlo[j]), "+r"(qhi[j]), "+r"(klo[j]), "+r"(vlo[j]));
  }
}

template <int ROT> __device__ __forceinline__ void halo_send(const float* acc, uint4* ho, uint32_t tag) {
#pragma unroll
  for (int j = 0; j < 7; j++) {
    uint32_t x[3];
#pragma unroll
    for (int e = 0; e < 3; e++) {
      const int i = 3 * j + e, y = (i % 10 + ROT) % 10, tk = y < 8 ? 8 + y : 18 + y, tv = y < 8 ? 16 + y : 20 + y;
      x[e] = i < 10 ? pack2(acc[4 * tk + 2], acc[4 * tk + 3]) : i < 20 ? movm(pack2(acc[4 * tv + 2], acc[4 * tv + 3])) : 0u;
    }
    asm volatile("st.relaxed.gpu.global.v4.u32 [%0], {%1, %2, %3, %4};" ::"l"(ho + 32 * j), "r"(x[0]), "r"(x[1]), "r"(x[2]), "r"(tag) : "memory");
  }
}

__device__ __forceinline__ void attention(float* acc, uint32_t sb, int b, int par, int w, int lane, uint32_t tag, uint32_t zero) {
  const int g = lane >> 2, t = lane & 3;
  uint32_t klo[10], khi[10], vlo[10], vhi[10], qlo[10], qhi[10], kpv[10], vpv[10];
  if (HALO_FIRST && w == 3 && b < NCTA - 8) {
    uint4* ho = g_halo + (b * 2 + par) * 224 + lane;
    if (tail_first(b & 7)) halo_send<8>(acc, ho, tag);
    else halo_send<0>(acc, ho, tag);
    TSIF(par == 0, 76);
    pin<120>(acc);
  }
  if (tail_first(b & 7)) pack_qkv<8>(acc, qlo, qhi, klo, khi, vlo, vhi);
  else pack_qkv<0>(acc, qlo, qhi, klo, khi, vlo, vhi);
  const uint32_t xa = sb + OFF_KVX + (par * 3) * 2560 + lane * 16;
  if (w < 3) {
    sts128(xa + w * 2560, khi[0], khi[1], khi[2], khi[3]);
    sts128(xa + w * 2560 + 512, khi[4], khi[5], khi[6], khi[7]);
    sts128(xa + w * 2560 + 1024, khi[8], khi[9], vhi[0], vhi[1]);
    sts128(xa + w * 2560 + 1536, vhi[2], vhi[3], vhi[4], vhi[5]);
    sts128(xa + w * 2560 + 2048, vhi[6], vhi[7], vhi[8], vhi[9]);
  } else if (!HALO_FIRST && b < NCTA - 8) {
    uint4* ho = g_halo + (b * 2 + par) * 224 + lane;
#pragma unroll
    for (int j = 0; j < 7; j++) {
      const uint32_t x0 = j < 4 ? khi[3 * j] : vhi[3 * j - 10], x1 = j < 3 ? khi[3 * j + 1] : vhi[3 * j - 9];
      const uint32_t x2 = j < 3 ? khi[3 * j + 2] : j < 6 ? vhi[3 * j - 8] : 0u;
      asm volatile("st.relaxed.gpu.global.v4.u32 [%0], {%1, %2, %3, %4};" ::"l"(ho + 32 * j), "r"(x0), "r"(x1), "r"(x2), "r"(tag) : "memory");
    }
  }
  TSIF(par == 0 && w == 1, 64);
  TSIF(par == 0 && w == 3 && !HALO_FIRST, 76);
#pragma unroll
  for (int j = 0; j < 10; j++) vlo[j] = movm(vlo[j]);
  const bool far0 = 2 * t > g, far1 = 2 * t + 1 > g;
  const uint32_t mfar = (far0 ? 0x0000FFFFu : 0u) | (far1 ? 0xFFFF0000u : 0u);
  float slo[4][2], shi[4][2], lg[2][2];
  uint32_t phi[4], plo[4], qml[4], qmh[4];
#pragma unroll
  for (int h = 0; h < 4; h++) {
    const int f = h == 0 ? 0 : h == 1 ? 3 : h == 2 ? 5 : 8, hf = h < 2 ? 2 : 7;
    const bool mine = (h & 1) ? t >= 2 : t < 2;
    qml[h] = mine ? qlo[hf] : 0u;
    qmh[h] = mine ? qhi[hf] : 0u;
    float a[4] = {0.f, 0.f, 0.f, 0.f}, c[4] = {0.f, 0.f, 0.f, 0.f};
    mma16816(a, qlo[f], qhi[f], qlo[f + 1], qhi[f + 1], klo[f], klo[f + 1]);
    mma16816(c, qlo[f], qhi[f], qlo[f + 1], qhi[f + 1], khi[f], khi[f + 1]);
    mma1688(a, qml[h], qmh[h], klo[hf]);
    mma1688(c, qml[h], qmh[h], khi[hf]);
    slo[h][0] = a[0];
    slo[h][1] = a[1];
    shi[h][0] = lg[h & 1][0] = far0 ? a[2] : c[2];
    shi[h][1] = lg[h & 1][1] = far1 ? a[3] : c[3];
    if (!ATT_MERGE && (h & 1)) softmax_two(lg, phi[h - 1], phi[h]);
  }
  TSIF(par == 0 && w == 1, 65);
  if (ATT_GATE == 3 && lane == 0) mbar_arrive(sb + OFF_BAR + 8 * B_ATT2 + (phi[3] & zero));
  wg_sync(1 + par);
  TSIF(par == 0 && w == 1, 66);
  const bool nohist = (w == 0) && (b < 8);
  const uint4* hp = g_halo + ((b - 8) * 2 + par) * 224 + lane;
  uint32_t tg[7];
  if (w > 0) {
    const uint4 v0 = lds128(xa + (w - 1) * 2560), v1 = lds128(xa + (w - 1) * 2560 + 512), v2 = lds128(xa + (w - 1) * 2560 + 1024);
    const uint4 v3 = lds128(xa + (w - 1) * 2560 + 1536), v4 = lds128(xa + (w - 1) * 2560 + 2048);
    kpv[0] = v0.x; kpv[1] = v0.y; kpv[2] = v0.z; kpv[3] = v0.w; kpv[4] = v1.x; kpv[5] = v1.y; kpv[6] = v1.z; kpv[7] = v1.w;
    kpv[8] = v2.x; kpv[9] = v2.y; vpv[0] = v2.z; vpv[1] = v2.w; vpv[2] = v3.x; vpv[3] = v3.y; vpv[4] = v3.z; vpv[5] = v3.w;
    vpv[6] = v4.x; vpv[7] = v4.y; vpv[8] = v4.z; vpv[9] = v4.w;
  } else if (nohist) {
#pragma unroll
    for (int j = 0; j < 10; j++) kpv[j] = vpv[j] = 0u;
  } else {
    TSIF(par == 0, 77);
    halo_read(kpv, vpv, tg, hp);
  }
  if (w == 0 && !nohist) {
    int spins = 0;
    while (true) {
      bool ok = true;
#pragma unroll
      for (int j = 0; j < 7; j++) ok = ok && tg[j] == tag;
      if (__all_sync(0xffffffffu, ok) || ++spins > SPIN_LIMIT) break;
      halo_read(kpv, vpv, tg, hp);
    }
    TSIF(par == 0, 79);
  }
#pragma unroll
  for (int h = 0; h < 4; h++) {
    const int f = h == 0 ? 0 : h == 1 ? 3 : h == 2 ? 5 : 8, hf = h < 2 ? 2 : 7;
    float a[4] = {0.f, 0.f, 0.f, 0.f};
    mma16816(a, qlo[f], qhi[f], qlo[f + 1], qhi[f + 1], kpv[f], kpv[f + 1]);
    mma1688(a, qml[h], qmh[h], kpv[hf]);
    const float ninf = __int_as_float(0xff800000);
    lg[h & 1][0] = far0 ? (nohist ? ninf : a[0]) : slo[h][0];
    lg[h & 1][1] = far1 ? (nohist ? ninf : a[1]) : slo[h][1];
    if (h & 1) {
      softmax_two(lg, plo[h - 1], plo[h]);
      if (ATT_MERGE) {
        const float lh[2][2] = {{shi[h - 1][0], shi[h - 1][1]}, {shi[h][0], shi[h][1]}};
        softmax_two(lh, phi[h - 1], phi[h]);
      }
    }
  }
  TSIF(par == 0 && w <= 1, 67 + w);
  if (ATT_GATE == 2 && lane == 0) mbar_arrive(sb + OFF_BAR + 8 * B_ATT2 + (plo[3] & zero));
  uint32_t ov[20];
#pragma unroll
  for (int hp = 0; hp < 2; hp++) {
    const int hf = hp ? 7 : 2;
    float sh[4] = {0.f, 0.f, 0.f, 0.f}, i0 = 0.f, i1 = 0.f;
#pragma unroll
    for (int e = 0; e < 2; e++) {
      const int h = 2 * hp + e, f = h == 0 ? 0 : h == 1 ? 3 : h == 2 ? 5 : 8;
      const uint32_t a0 = plo[h] & mfar, a2 = plo[h] & ~mfar, a3 = phi[h] & mfar, c1 = phi[h] & ~mfar;
      float sum[4] = {0.f, 0.f, 0.f, 0.f};
      mma1688(sum, plo[h], phi[h], 0x3F803F80u);
      const float r0 = rcp(sum[0]), r1 = rcp(sum[2]);
#pragma unroll
      for (int j = f; j < f + 2; j++) {
        float o[4] = {0.f, 0.f, 0.f, 0.f};
        mma16816(o, a0, 0u, a2, a3, vpv[j], vlo[j]);
        mma1688(o, 0u, c1, vhi[j]);
        ov[2 * j] = pack2(o[0] * r0, o[1] * r0);
        ov[2 * j + 1] = pack2(o[2] * r1, o[3] * r1);
      }
      const bool mine = e ? g >= 4 : g < 4;
      mma16816(sh, a0, 0u, a2, a3, mine ? vpv[hf] : 0u, mine ? vlo[hf] : 0u);
      mma1688(sh, 0u, c1, mine ? vhi[hf] : 0u);
      if (e == 0 || t >= 2) {
        i0 = r0;
        i1 = r1;
      }
    }
    ov[2 * hf] = pack2(sh[0] * i0, sh[1] * i0);
    ov[2 * hf + 1] = pack2(sh[2] * i1, sh[3] * i1);
  }
  if (ATT_GATE == 4 && lane == 0) mbar_arrive(sb + OFF_BAR + 8 * B_ATT2 + (ov[19] & zero));
  TS(32 + 4 * par + w);
  mbar_wait(sb + OFF_BAR + 8 * B_P1, 0);
  const uint32_t oa = sb + OFF_OA + (lane >> 4) * 2048 + (32 * w + 2 * (lane & 15) + par) * 16;
#pragma unroll
  for (int j = 0; j < 5; j++) stsm4(oa + 4096 * j, ov + 4 * j);
  TSIF(par == 0 && w == 0, 120);
  fence_async_smem();
  TSIF(par == 0 && w == 0, 121);
  __syncwarp();
  if (lane == 0) mbar_arrive(sb + OFF_BAR + 8 * B_ATTN);
  TSM(w == 0 || w == 2, 122 + par + (w == 2 ? 3 : 0));
}

struct Maps {
  CUtensorMap x, wm, wt, k, v, y, wo, qm, qt, om, ot, u, wh;
};

__device__ __forceinline__ void load_stage(uint32_t sb, int kb, int b, const Maps& m) {
  const uint32_t st = sb + (kb & 3) * STAGE_BYTES, bar = sb + OFF_BAR + 8 * (B_FULL1 + (kb & 3));
  const int r = b >> 3, hg = b & 7, slab = kb - KV_KB;
  const bool kv = slab >= 0 && slab < 5;
  const uint32_t kbar = sb + OFF_BAR + 8 * (B_KV + slab), dst = sb + OFF_KVS + slab * KVS_BYTES;
  mbar_expect_tx(bar, STAGE_BYTES);
  if (kv) mbar_expect_tx(kbar, KVS_BYTES);
  tma_3d(st, &m.x, 64 * kb, 64 * r, 0, bar);
  if (kv && KV_MIX) tma_3d(dst, &m.k, 0, 32 * (b >> 1) - 3, 2 * slab + (b & 1), kbar);
  tma_3d(st + ST_W, &m.wm, 80 * hg + (tail_first(hg) ? 16 : 0), 64 * kb, 0, bar);
  if (kv && KV_MIX) tma_3d(dst + KVS_V, &m.v, 0, 32 * (b >> 1), 2 * slab + (b & 1), kbar);
  tma_3d(st + ST_WT, &m.wt, 80 * hg + (tail_first(hg) ? 0 : 64), 64 * kb, 0, bar);
  if (kv && !KV_MIX) tma_3d(dst, &m.k, 0, 32 * (b >> 1) - 3, 2 * slab + (b & 1), kbar);
  if (kv && !KV_MIX) tma_3d(dst + KVS_V, &m.v, 0, 32 * (b >> 1), 2 * slab + (b & 1), kbar);
}

__global__ void __launch_bounds__(NTHR, 1) fused_kernel(const __grid_constant__ Maps m, const Params p) {
  extern __shared__ __align__(1024) uint8_t smem[];
  const uint32_t sb = (uint32_t)__cvta_generic_to_shared(smem);
  const uint32_t bars = sb + OFF_BAR;
  const int tid = threadIdx.x, lane = tid & 31;
  int b = blockIdx.x;
  if (BMAP == 1) b = (((b & 63) >> 3) * 2 + (b & 1)) * 8 + (((b < 64 ? 0x6521 : 0x7430) >> (4 * ((b >> 1) & 3))) & 7);
  if (BMAP == 2) b = ((b & 63) >> 2) * 8 + (((b < 64 ? 0x6521 : 0x7430) >> (4 * (b & 3))) & 7);
  if (BMAP == 3) b = (((b & 63) >> 3) * 2 + (b & 1)) * 8 + (((b < 64 ? 0x7430 : 0x6521) >> (4 * ((b >> 1) & 3))) & 7);
  if (BMAP == 4) b = (((b >> 4) * 2 + (b & 1)) * 8) + ((b >> 1) & 7);
  if (BMAP == 5) b = 127 - b;
  const int r = b >> 3, hg = b & 7;

  if (tid == T_ISSUE) {
    TSM(true, 0);
#pragma unroll
    for (int i = 0; i < 4; i++) mbar_init(bars + 8 * (B_FULL1 + i), 1);
#pragma unroll
    for (int i = 0; i < 3; i++) mbar_init(bars + 8 * (B_KV + i), 1);
    fence_async_smem();
    if (T0_SPLIT) {
      const int cm = 80 * hg + (tail_first(hg) ? 16 : 0);
      mbar_init(bars + 8 * B_F0, 1);
      mbar_init(bars + 8 * (B_F0 + 1), 1);
      fence_async_smem();
      mbar_expect_tx(bars + 8 * B_F0, T0_SPLIT == 2 ? ST_W + 12288 : ST_WT);
      tma_3d(sb, &m.x, 0, 64 * r, 0, bars + 8 * B_F0);
      if (T0_SPLIT == 2) {
        tma_3d(sb + ST_W, &m.wh, cm, 0, 0, bars + 8 * B_F0);
        mbar_expect_tx(bars + 8 * (B_F0 + 1), 12288);
        tma_3d(sb + ST_W + 12288, &m.wh, cm, 32, 0, bars + 8 * (B_F0 + 1));
      } else {
        tma_3d(sb + ST_W, &m.wm, cm, 0, 0, bars + 8 * B_F0);
      }
      mbar_expect_tx(bars + 8 * B_FULL1, STAGE_BYTES - ST_WT);
      tma_3d(sb + ST_WT, &m.wt, 80 * hg + (tail_first(hg) ? 0 : 64), 0, 0, bars + 8 * B_FULL1);
    }
#pragma unroll 1
    for (int kb = T0_SPLIT ? 1 : 0; kb <= PRE2; kb++) load_stage(sb, kb, b, m);
  } else if (tid >= T_PF && tid < T_PF + 12) {
    tm_prefetch(&m.x + (tid - T_PF));
  } else if (tid == T_INIT) {
#pragma unroll
    for (int i = 0; i < 4; i++) mbar_init(bars + 8 * (B_EMPTY1 + i), 8);
#pragma unroll
    for (int i = 0; i < 8; i++) mbar_init(bars + 8 * (B_FULL2 + i), 1);
#pragma unroll
    for (int i = 0; i < 4; i++) mbar_init(bars + 8 * (B_EMPTY2 + i), 8);
#pragma unroll
    for (int i = 0; i < 4; i++) mbar_init(bars + 8 * (B_U + i), 1);
    mbar_init(bars + 8 * B_HA, 4);
    mbar_init(bars + 8 * B_GATE, 4);
    mbar_init(bars + 8 * B_HB, 1);
    mbar_init(bars + 8 * B_KVD, 4);
    mbar_init(bars + 8 * B_QF, 1);
    mbar_init(bars + 8 * B_ATTN, 8);
    mbar_init(bars + 8 * B_ATT2, 8);
    mbar_init(bars + 8 * B_P1, 8);
    mbar_init(bars + 8 * B_C34, 1);
    mbar_init(bars + 8 * B_YRB, 1);
#pragma unroll
    for (int i = 0; i < 5; i++) mbar_init(bars + 8 * (B_YST + i), 4);
#pragma unroll
    for (int i = 0; i < 3; i++) mbar_init(bars + 8 * (B_US + i), U_TMA ? 4 : i == 2 ? 20 : 1);
    mbar_init(bars + 8 * B_YSIG, 1);
    mbar_init(bars + 8 * B_YFULL, 1);
    mbar_init(bars + 8 * B_EPOCH, 1);
    mbar_init(bars + 8 * B_PREP, 4);
    mbar_init(bars + 8 * B_USIG, 1);
    mbar_init(bars + 8 * B_WST, 1);
#pragma unroll
    for (int i = 3; i < 5; i++) mbar_init(bars + 8 * (B_KV + i), 1);
    mbar_init(bars + 8 * B_E3, 8);
    mbar_init(bars + 8 * B_LAST, 1);
    mbar_init(bars + 8 * B_OSIG, 1);
    mbar_init(bars + 8 * B_WOP, 1);
    fence_async_smem();
  }
  const int warp = __shfl_sync(0xffffffffu, tid >> 5, 0), wg = warp >> 2, w = warp & 3;
  __syncthreads();

  if (wg == 3) {
    asm volatile("setmaxnreg.dec.sync.aligned.u32 56;");
    if (w == 0) {
      if (lane == 0) {
#pragma unroll 1
        for (int kb = 1 + PRE2; kb < 10; kb++) {
          if (kb >= 4) mbar_wait(bars + 8 * (kb == 7 ? B_E3 : B_EMPTY1 + (kb & 3)), (kb >> 3) & 1);
          TSIF(kb >= 4, 44 + kb);
          load_stage(sb, kb, b, m);
          TSIF(kb == 3, 60);
          if (kb == TRIG_KB) mbar_arrive(bars + 8 * B_LAST);
        }
        mbar_wait(bars + 8 * B_WOP, 0);
        mbar_wait(bars + 8 * WL_TRIG, 0);
        mbar_wait(bars + 8 * B_EPOCH, 0);
        flag_wait(g_cnt + C_W + 32 * hg, (lds32(sb + OFF_EPOCH) + 1) * 16);
        TS(30);
#pragma unroll 1
        for (int j = 0; j < 8; j++) {
          if (j >= 6) mbar_wait(bars + 8 * (B_EMPTY2 + j - 6), 0);
          if (j == 4) mbar_wait(bars + 8 * B_ATTN, 0);
          TSIF(j >= 6, 100 + j);
          if (RF_GATE && j == 6) mbar_wait(bars + 8 * B_YSIG, 0);
          mbar_expect_tx(bars + 8 * (B_FULL2 + j), j == 0 ? WO_BYTES : j == 5 ? O_BYTES + WO_BYTES + 512 : O_BYTES + WO_BYTES);
          bulk_load(sb + off_w(j), g_WO + (hg * 8 + step_src(hg, j)) * 800, WO_BYTES, bars + 8 * (B_FULL2 + j));
        }
        mbar_wait(bars + 8 * (B_EMPTY2 + Q_SLOT), 0);
        mbar_expect_tx(bars + 8 * B_QF, O_BYTES);
        tma_2d(sb + OFF_QS, &m.qm, 80 * hg, 128 * r, bars + 8 * B_QF);
        if (!QBOX) tma_2d(sb + OFF_QT, &m.qt, 80 * hg + 64, 128 * r, bars + 8 * B_QF);
      }
    } else if (w == 1) {
      unsigned epoch = 0;
      if (lane == 0) {
        epoch = atomicAdd(g_cnt + C_LAUNCH, 1u) / NCTA;
        asm volatile("st.shared.u32 [%0], %1;" ::"r"(sb + OFF_EPOCH), "r"(epoch) : "memory");
        mbar_arrive(bars + 8 * B_EPOCH);
        mbar_wait(bars + 8 * B_KVD, 0);
        mbar_expect_tx(bars + 8 * B_HB, 5 * 4096);
#pragma unroll 1
        for (int c = 0; c < 5; c++) {
          if (c == 3) mbar_wait(bars + 8 * B_S3, 0);
          bulk_load(sb + off_ch(c) + U_BYTES, p.ssm_k + (5 * b + c) * SEQ, 4096, bars + 8 * B_HB);
        }
#pragma unroll
        for (int c = 0; c < 4; c++) mbar_expect_tx(bars + 8 * (B_U + c), c < 3 ? U_BYTES : 2 * U_BYTES);
        const uint4* usrc = g_U + 5 * b * U_PITCH;
        mbar_wait(bars + 8 * B_USIG, 0);
        flag_wait(g_cnt + C_PREP + 32 * (b & 15), (epoch + 1) * NCTA);
        TS(23);
#pragma unroll
        for (int c = 0; c < 5; c++) {
          if (c == 3 && U_TRIM) mbar_wait(bars + 8 * (B_U + 2), 0);
          bulk_load(sb + off_ch(c), usrc + c * U_PITCH, U_BYTES, bars + 8 * (B_U + (c < 3 ? c : 3)));
          TSIF(c == 0 || c == 4, 116 + (c >> 2));
        }
      }
      epoch = __shfl_sync(0xffffffffu, epoch, 0);
      if (lane < 8) {
        const int src = (b & ~7) | step_src(hg, lane);
        mbar_wait(bars + 8 * OP_TRIG, 0);
        TS(20);
        bool seen = false;
#pragma unroll 1
        for (int spins = 0; spins < SPIN_LIMIT; spins++) {
          const bool now = !seen && (int)(flag_read(g_cnt + C_O + 32 * src) - (epoch + 1)) >= 0;
          if (now && lane >= 1 && lane < 4) bulk_load(sb + off_o(lane), g_O + src * 1280, O_BYTES, bars + 8 * (B_FULL2 + lane));
          seen = seen || now;
          if (__all_sync(0xff, seen)) break;
        }
        TS(21);
        if (lane == 5) bulk_load(sb + OFF_GATE, g_gate + 128 * r, 512, bars + 8 * (B_FULL2 + 5));
#pragma unroll 1
        for (int j = 4; j < 8; j++) {
          if (lane == j) {
            mbar_wait(bars + 8 * (j < 6 ? B_C34 : B_EMPTY2 + j - 6), 0);
            if (RF_GATE && j == 6) mbar_wait(bars + 8 * B_YSIG, 0);
            bulk_load(sb + off_o(j), g_O + src * 1280, O_BYTES, bars + 8 * (B_FULL2 + j));
          }
          __syncwarp(0xff);
        }
        TS(22);
      }
    } else if (w == 2) {
      mbar_wait(bars + 8 * B_PREP, 0);
      flag_signal(g_cnt + C_PREP, 16, lane);
      TS(25);
      if (lane == 0) mbar_arrive(bars + 8 * B_USIG);
      mbar_wait(bars + 8 * B_GATE, 0);
      if (G_TMA) {
        if (lane == 0) {
          asm volatile("cp.async.bulk.global.shared::cta.bulk_group [%0], [%1], 64;\ncp.async.bulk.commit_group;\n"
                       "cp.async.bulk.wait_group.read 0;" ::"l"(g_gate + 16 * b), "r"(sb + OFF_GATE + 64 * hg) : "memory");
          bulk_load(sb + OFF_GATE + 64 * hg, g_gate + 16 * b, 64, bars + 8 * B_ORB);
        }
      } else if (((NOMB & 1) || O_RB) && lane == 0) {
        asm volatile("fence.release.gpu;" ::: "memory");
      }
      mbar_wait(bars + 8 * B_ATTN, 0);
      if (lane == 0) {
        if (O_DEFER) mbar_wait(bars + 8 * (B_U + 3), 0);
        asm volatile("cp.async.bulk.global.shared::cta.bulk_group [%0], [%1], 20480;\ncp.async.bulk.commit_group;"
                     ::"l"(g_O + b * 1280), "r"(sb + OFF_OA) : "memory");
        if (O_RB == 2) {
          asm volatile("cp.async.bulk.wait_group.read 0;" ::: "memory");
          mbar_expect_tx(bars + 8 * B_ORB, O_BYTES + 64 * G_TMA);
          bulk_load(sb + OFF_OA, g_O + b * 1280, O_BYTES, bars + 8 * B_ORB);
          mbar_wait(bars + 8 * B_ORB, 0);
          flag_bump(g_cnt + C_O + 32 * b);
        } else if (O_RB) asm volatile("cp.async.bulk.wait_group.read 0;" ::: "memory");
        else asm volatile("cp.async.bulk.wait_group 0;\nfence.proxy.async.global;" ::: "memory");
      }
      TS(74);
      if (O_RB == 2) {
      } else if (O_RB) {
        __syncwarp();
        unsigned v[5];
#pragma unroll
        for (int c = 0; c < 5; c++) v[c] = flag_read(reinterpret_cast<const unsigned*>(g_O + b * 1280 + 256 * c + 8 * lane + 7));
        const unsigned dep = __reduce_or_sync(0xffffffffu, (v[0] ^ v[1] ^ v[2] ^ v[3] ^ v[4]) & p.zero);
        if (lane == 0) flag_bump(g_cnt + C_O + 32 * b + dep);
      } else if (!(NOMB & 1)) flag_signal(g_cnt + C_O + 32 * b, 1, lane);
      else if (lane == 0) flag_bump(g_cnt + C_O + 32 * b);
      TS(26);
      if (lane == 0) mbar_arrive(bars + 8 * B_OSIG);

    } else {
      if (lane == 0) {
        uint4* dst = g_WO + (hg * 8 + (r >> 1)) * 800 + (r & 1) * 80;
        if (WPF) {
          mbar_wait(bars + 8 * WPF, 0);
          if (WPF_LIN)
            asm volatile("cp.async.bulk.prefetch.L2.global [%0], 6400;" ::"l"(p.wo + b * 3200) : "memory");
          else
            asm volatile("cp.async.bulk.prefetch.tensor.3d.L2.global [%0, {%1, %2, %3}];" ::"l"(&m.wo), "r"(0), "r"(40 * r), "r"(5 * hg) : "memory");
        }
        mbar_wait(bars + 8 * B_P1, 0);
        mbar_wait(bars + 8 * WB_TRIG, 0);
        mbar_expect_tx(bars + 8 * B_WST, WO_BYTES / 2);
        tma_3d(sb + OFF_WS, &m.wo, 0, 40 * r, 5 * hg, bars + 8 * B_WST);
        mbar_wait(bars + 8 * B_WST, 0);
        mbar_wait(bars + 8 * WO_TRIG, 0);
#pragma unroll 1
        for (int n = 0; n < 5; n++)
          asm volatile("cp.async.bulk.global.shared::cta.bulk_group [%0], [%1], 1280;" ::"l"(dst + 160 * n), "r"(sb + OFF_WS + 1280 * n) : "memory");
        if (W_RB) {
          asm volatile("cp.async.bulk.commit_group;\ncp.async.bulk.wait_group.read 0;" ::: "memory");
          mbar_expect_tx(bars + 8 * B_WST, WO_BYTES / 2);
#pragma unroll 1
          for (int n = 0; n < 5; n++) bulk_load(sb + OFF_WS + 1280 * n, dst + 160 * n, 1280, bars + 8 * B_WST);
          mbar_wait(bars + 8 * B_WST, 1);
        } else {
          asm volatile("cp.async.bulk.commit_group;\ncp.async.bulk.wait_group 0;\nfence.proxy.async.global;" ::: "memory");
          if (!(NOMB & 4)) asm volatile("fence.release.gpu;" ::: "memory");
        }
        flag_bump(g_cnt + C_W + 32 * hg);
        mbar_arrive(bars + 8 * B_WOP);
        TS(71);
        mbar_expect_tx(bars + 8 * B_C34, 3 * U_BYTES);
        mbar_expect_tx(bars + 8 * B_YRB, 2 * U_BYTES);
#pragma unroll 1
        for (int c = 0; c < 5; c++) {
          mbar_wait(bars + 8 * (B_YST + c), 0);
          asm volatile("cp.async.bulk.global.shared::cta.bulk_group [%0], [%1], 4096;\ncp.async.bulk.commit_group;\n"
                       "cp.async.bulk.wait_group.read 0;" ::"l"(g_Y + (5 * b + c) * Y_PITCH), "r"(sb + off_ch(c)) : "memory");
          bulk_load(sb + off_ch(c), g_Y + (5 * b + c) * Y_PITCH, U_BYTES, bars + 8 * (c < 3 ? B_C34 : B_YRB));
        }
        TS(75);
        mbar_wait(bars + 8 * B_C34, 0);
        mbar_wait(bars + 8 * B_YRB, 0);
        flag_bump(g_cnt + C_Y + 32 * (b >> 4));
        TS(27);
        mbar_arrive(bars + 8 * B_YSIG);
        mbar_expect_tx(bars + 8 * B_YFULL, 20480);
        flag_wait(g_cnt + C_Y + 32 * hg, (lds32(sb + OFF_EPOCH) + 1) * 16);
        TS(24);
        tma_2d(sb + OFF_YT, &m.y, 128 * r, 80 * hg, bars + 8 * B_YFULL);
        tma_2d(sb + OFF_YT + 10240, &m.y, 128 * r + 64, 80 * hg, bars + 8 * B_YFULL);
      }
    }
  } else {
    asm volatile("setmaxnreg.inc.sync.aligned.u32 152;");
    if (wg < 2) {
      float acc[120];
#pragma unroll
      for (int i = 0; i < 120; i++) acc[i] = 0.f;
      const uint32_t da = desc_lo(sb + wg * 8192, 16), db = desc_lo(sb + ST_W, 8192), dc = desc_lo(sb + ST_WT, 2048);
      if (PW1) pin<120>(acc);
      if (T0_SPLIT) {
        mbar_wait(bars + 8 * B_F0, 0);
        TSIF(w == 0 && wg == 0, 84);
        wg_fence();
#pragma unroll
        for (int k = 0; k < 4; k++) {
          if (T0_SPLIT == 2 && k == 2) {
            wg_commit();
            mbar_wait(bars + 8 * (B_F0 + 1), 0);
            wg_fence();
          }
          WgSST<192>::mma<HI_SW128, HI_SW128>(acc, da + 2 * k, T0_SPLIT == 2 ? desc_lo(sb + ST_W, 4096) + 128 * (k & 1) + 768 * (k >> 1) : db + 128 * k, 1);
        }
        wg_commit();
        mbar_wait(bars + 8 * B_FULL1, 0);
        wg_fence();
#pragma unroll
        for (int k = 0; k < 4; k++) WgSST<48>::mma<HI_SW128, HI_SW32>(acc + 96, da + 2 * k, dc + 32 * k, 1);
        wg_commit();
      }
      if (PW1 == 2) mbar_wait(bars + 8 * B_FULL1, 0);
#pragma unroll 1
      for (int kb = T0_SPLIT ? 1 : 0; kb < 10; kb++) {
        mbar_wait(bars + 8 * (B_FULL1 + (kb & 3)), (kb >> 2) & 1);
        const uint32_t so = (kb & 3) * (STAGE_BYTES >> 4);
        wg_fence();
#pragma unroll
        for (int k = 0; k < 4; k++) {
          WgSST<192>::mma<HI_SW128, HI_SW128>(acc, da + so + 2 * k, db + so + 128 * k, 1);
          WgSST<48>::mma<HI_SW128, HI_SW32>(acc + 96, da + so + 2 * k, dc + so + 32 * k, 1);
        }
        wg_commit();
        wg_wait<1>();
        if (kb > 0 && lane == 0) mbar_arrive(bars + 8 * (kb == 4 ? B_E3 : B_EMPTY1 + ((kb - 1) & 3)));
      }
      mbar_wait(bars + 8 * B_EPOCH, 0);
      const uint32_t tag = lds32(sb + OFF_EPOCH) + 1;
      mbar_wait(bars + 8 * B_S3, 0);
      wg_wait<0>();
      pin<120>(acc);
      if (lane == 0) mbar_arrive(bars + 8 * B_P1);
      TSM(w == 0, 3 + wg);
      attention(acc, sb, b, wg, w, lane, tag, p.zero);
    } else {
      const int tw = tid & 127, chl = 64 * (b & 1) + 8 * w + (lane >> 2);
      uint4* up = g_U + chl * U_PITCH + ((4 * (b >> 1) + (lane & 3)) ^ ((b >> 2) & 1));
      uint2 sw[10];
      uint32_t dv = 0;
      if (lane < 5) dv = __ldg(reinterpret_cast<const unsigned short*>(p.ssm_D) + 5 * b + lane);
#pragma unroll
      for (int i = 0; i < 10; i++) sw[i] = ldg64(reinterpret_cast<const uint2*>(p.shift_k) + chl + 128 * (i >> 1) + 32 * (i & 1));
      uint32_t tab[12];
      uint32_t tt[2];
      fft_tables(tab, tw);
      fft_twiddles(tt, tw);
      uint4 res[10];
#pragma unroll
      for (int i = 0; i < 10; i++) res[i] = make_uint4(0, 0, 0, 0);
#pragma unroll 1
      for (int slab = 0; slab < 5; slab++) {
#pragma unroll
        for (int i = 0; i < 8; i++) res[i] = res[i + 2];
        prep_slab(res + 8, sw, sb, slab, w, lane);
        TSIF(w == 0, 99 + 4 * slab);
#pragma unroll
        for (int i = 0; i < 8; i++) sw[i] = sw[i + 2];
      }
      TSIF(w == 0, 28);
      __syncwarp();
      if (lane == 0) mbar_arrive(bars + 8 * B_KVD + ((res[8].x ^ res[9].x) & p.zero));
      mbar_wait(bars + 8 * B_KVD, 0);
      fft_tables_store(tab, sb, tw);
      mbar_wait(bars + 8 * B_LAST, 0);
#pragma unroll
      for (int i = 0; i < 10; i++) up[(128 * (i >> 1) + 32 * (i & 1)) * U_PITCH] = res[i];
      __syncwarp();
      if (lane == 0) mbar_arrive(bars + 8 * B_PREP);
      TSIF(w == 0 && !U_TMA, 5);
      mbar_wait(bars + 8 * (G_AFTER ? B_USIG : B_LAST), 0);
      prep_gate(p, sb, b, w, lane);
      __syncwarp();
      if (lane == 0) mbar_arrive(bars + 8 * B_GATE);
      TSIF(w == 0, 72);
      mbar_wait(bars + 8 * B_HB, 0);
      TSIF(w == 0, 2);
      const uint32_t ha = sb + U_BYTES + ((tw >> 3) * 16 + 8 + (tw & 7)) * 16;
      uint4 hv[5];
#pragma unroll
      for (int c = 0; c < 5; c++) hv[c] = lds128(ha + off_ch(c));
      __syncwarp();
#pragma unroll
      for (int c = 0; c < 5; c++) sts128((ha ^ 16) + off_ch(c), hv[c].x, hv[c].y, hv[c].z, hv[c].w);
      asm volatile("st.shared.v2.u32 [%0], {%1, %2};" ::"r"(sb + OFF_TT + 8 * tw), "r"(tt[0]), "r"(tt[1]) : "memory");
      if (tw < 5) asm volatile("st.shared.f32 [%0], %1;" ::"r"(sb + OFF_D + 4 * tw), "f"(bf_lo(dv) * 0.125f) : "memory");
      fence_async_smem();
      __syncwarp();
      if (lane == 0) mbar_arrive(bars + 8 * B_HA);
      TSIF(w == 0, 6);
    }

    FftConst fc;
    TSM(w == 0 && wg == 0, 104);
    mbar_wait(bars + 8 * B_HA, 0);
    fft_matrices(fc, sb, w, lane);
    TSM(w == 0 && wg == 0, 105);
    TSM(w == 0 && wg == 2, 124);
#pragma unroll 1
    for (uint32_t tasks = wg == 0 ? TASK0 : wg == 1 ? TASK1 : TASK2; tasks; tasks >>= 4) {
      const int c = (tasks & 7) - 1;
      conv_channel(fc, sb, c, wg, w, lane);
      if (lane == 0) mbar_arrive(bars + 8 * (B_YST + c));
      TSM(w == 0, 10 + c);
    }

    if (wg < 2) {
      const int g = lane >> 2;
      float acc[40];
#pragma unroll
      for (int i = 0; i < 40; i++) acc[i] = 0.f;
      const uint32_t da = desc_lo(sb + wg * 1024, 2048), db = desc_lo(sb, 2560);
      mbar_wait(bars + 8 * (O_RB == 2 ? B_ORB : B_ATTN), 0);
      if (PW2) mbar_wait(bars + 8 * B_FULL2, 0);
      mbar_wait(bars + 8 * B_CVD, 0);
      TSM(w == 0, 15 + wg);
#pragma unroll 1
      for (int j = 0; j < 8; j++) {
        mbar_wait(bars + 8 * (B_FULL2 + j), 0);
        TSM(w == 0 && wg == 0, 44 + (j < 4 ? j : j + 6));
        const uint32_t oa = da + (off_o(j) >> 4), ob = db + (off_w(j) >> 4);
        wg_fence();
#pragma unroll
        for (int k = 0; k < 5; k++) WgSST<80>::mma<HI_NONE, HI_SW32>(acc, oa + 256 * k, ob + 32 * k, 1);
        wg_commit();
        wg_wait<1>();
        if (j >= 1 && j <= Q_SLOT + 1 && lane == 0) mbar_arrive(bars + 8 * (B_EMPTY2 + j - 1));
      }
      TSIF(w == 0 && wg == 0, 113);
      const int tr = 64 * wg + 16 * w + (lane & 15);
      const uint32_t fm = sb + OFF_QS + tr * 128, fx = (lane >> 4) ^ (tr & 7), fq = sb + OFF_QS + tr * 160 + (lane >> 4) * 16;
      const uint32_t ft = sb + OFF_QT + tr * 32 + (((lane >> 4) ^ (tr >> 2)) & 1) * 16;
      const float g0 = __uint_as_float(lds32(sb + OFF_GATE + (64 * wg + 16 * w + g) * 4));
      const float g1 = __uint_as_float(lds32(sb + OFF_GATE + (64 * wg + 16 * w + 8 + g) * 4));
      const uint32_t ga = pack2(g0, g0), gb = pack2(g1, g1);
      const uint32_t na = pack2(1.f - g0, 1.f - g0), nb = pack2(1.f - g1, 1.f - g1);

      uint32_t qf[20];
      mbar_wait(bars + 8 * B_QF, 0);
      TSM(w == 0 && wg == 0, 99);
#pragma unroll
      for (int j = 0; j < 5; j++) ldsm4(qf + 4 * j, QBOX ? fq + 32 * j : j < 4 ? fm + ((fx ^ (2 * j)) << 4) : ft);
      if (FUSE_MIX) {
#pragma unroll
        for (int i = 0; i < 20; i++) {
          qf[i] = bmul((i & 1) ? gb : ga, qf[i]);
          asm volatile("" : "+r"(qf[i]));
        }
      }
      wg_wait<0>();
      pin<40>(acc);
      TSM(w == 0, 17 + wg);
      uint32_t pb[20];
#pragma unroll
      for (int j = 0; j < 10; j++) {
        pb[2 * j] = bmul(na, pack2(acc[4 * j], acc[4 * j + 1]));
        pb[2 * j + 1] = bmul(nb, pack2(acc[4 * j + 2], acc[4 * j + 3]));
        asm volatile("" : "+r"(pb[2 * j]), "+r"(pb[2 * j + 1]));
      }
      const uint32_t ya = sb + OFF_YT + wg * 10240 + ((lane >> 4) * 8 + (lane & 7)) * 128 +
                          (((2 * w + (((lane >> 3) & 1) ^ wg)) ^ (lane & 7)) << 4);
      mbar_wait(bars + 8 * B_YFULL, 0);
      TSM(w == 0 && wg == 0, 19);
#pragma unroll
      for (int j = 0; j < 5; j++) {
        uint32_t y[4];
        ldsm4t(y, ya + 2048 * j);
#pragma unroll
        for (int i = 0; i < 4; i++)
          qf[4 * j + i] = FUSE_MIX ? bfma(qf[4 * j + i], y[i], pb[4 * j + i]) : badd(bmul((i & 1) ? gb : ga, bmul(qf[4 * j + i], y[i])), pb[4 * j + i]);
      }
#pragma unroll
      for (int j = 0; j < 5; j++) stsm4(QBOX ? fq + 32 * j : j < 4 ? fm + ((fx ^ (2 * j)) << 4) : ft, qf + 4 * j);
      fence_async_smem();
      __syncwarp();
      if (lane == 0) {
        const int row = 64 * wg + 16 * w;
        asm volatile("cp.async.bulk.tensor.2d.global.shared::cta.bulk_group [%0, {%2, %3}], [%1];"
                     ::"l"(&m.om), "r"(sb + OFF_QS + row * (QBOX ? 160 : 128)), "r"(80 * hg), "r"(128 * r + row) : "memory");
        if (!QBOX) asm volatile("cp.async.bulk.tensor.2d.global.shared::cta.bulk_group [%0, {%2, %3}], [%1];"
                     ::"l"(&m.ot), "r"(sb + OFF_QT + row * 32), "r"(80 * hg + 64), "r"(128 * r + row) : "memory");
        asm volatile("cp.async.bulk.commit_group;\ncp.async.bulk.wait_group.read 0;" ::: "memory");
      }
      TSM(w == 0 || w == 3, 40 + 2 * wg + (w & 1));
      if (ENDBAR) asm volatile("bar.sync 15, 256;" ::: "memory");
    }
  }
}

typedef CUresult (*EncodeFn)(CUtensorMap*, CUtensorMapDataType, cuuint32_t, void*, const cuuint64_t*, const cuuint64_t*,
                             const cuuint32_t*, const cuuint32_t*, CUtensorMapInterleave, CUtensorMapSwizzle,
                             CUtensorMapL2promotion, CUtensorMapFloatOOBfill);

void encode(EncodeFn fn, CUtensorMap* tm, const void* base, int rank, const cuuint64_t* dims, const cuuint64_t* strides,
            const cuuint32_t* box, CUtensorMapSwizzle swz) {
  const cuuint32_t ones[3] = {1, 1, 1};
  fn(tm, CU_TENSOR_MAP_DATA_TYPE_BFLOAT16, rank, const_cast<void*>(base), dims, strides, box, ones,
     CU_TENSOR_MAP_INTERLEAVE_NONE, swz, CU_TENSOR_MAP_L2_PROMOTION_L2_128B, CU_TENSOR_MAP_FLOAT_OOB_FILL_NONE);
}

}

extern "C" void kernel_launch(void* const* d_in, const int* in_sizes, int n_in, void* d_out, int out_size) {
  (void)in_sizes; (void)n_in; (void)out_size;
  Params p;
  p.q = (const __nv_bfloat16*)d_in[0];
  p.k = (const __nv_bfloat16*)d_in[1];
  p.v = (const __nv_bfloat16*)d_in[2];
  p.shift_k = (const __nv_bfloat16*)d_in[3];
  p.ssm_k = (const __nv_bfloat16*)d_in[4];
  p.ssm_D = (const __nv_bfloat16*)d_in[5];
  p.wqkv = (const __nv_bfloat16*)d_in[7];
  p.wo = (const __nv_bfloat16*)d_in[8];
  p.gate_w = (const __nv_bfloat16*)d_in[9];
  p.out = (__nv_bfloat16*)d_out;
  p.zero = 0;

  static EncodeFn fn = nullptr;
  static void *yaddr = nullptr, *uaddr = nullptr;
  if (!fn) {
    cudaDriverEntryPointQueryResult qr;
    void* f = nullptr;
    cudaGetDriverEntryPoint("cuTensorMapEncodeTiled", &f, cudaEnableDefault, &qr);
    fn = (EncodeFn)f;
    cudaGetSymbolAddress(&yaddr, g_Y);
    cudaGetSymbolAddress(&uaddr, g_U);
    cudaFuncSetAttribute(fused_kernel, cudaFuncAttributeMaxDynamicSharedMemorySize, SMEM_BYTES);
  }
  Maps m;
  {
    const cuuint64_t dims[3] = {640, 1024, 2}, st[2] = {2560, 1280};
    const cuuint32_t box[3] = {64, 64, 2};
    encode(fn, &m.x, p.q, 3, dims, st, box, CU_TENSOR_MAP_SWIZZLE_128B);
  }
  {
    const cuuint64_t dims[3] = {640, 640, 3}, st[2] = {3840, 1280};
    const cuuint32_t box[3] = {64, 64, 3}, boxt[3] = {16, 64, 3};
    encode(fn, &m.wm, p.wqkv, 3, dims, st, box, CU_TENSOR_MAP_SWIZZLE_128B);
    encode(fn, &m.wt, p.wqkv, 3, dims, st, boxt, CU_TENSOR_MAP_SWIZZLE_32B);
    const cuuint32_t boxh[3] = {64, 32, 3};
    encode(fn, &m.wh, p.wqkv, 3, dims, st, boxh, CU_TENSOR_MAP_SWIZZLE_128B);
  }
  {
    const cuuint64_t dims[3] = {64, 2048, 10}, st[2] = {1280, 128};
    const cuuint32_t boxk[3] = {64, 35, 1}, boxv[3] = {64, 32, 1};
    encode(fn, &m.k, p.k, 3, dims, st, boxk, CU_TENSOR_MAP_SWIZZLE_128B);
    encode(fn, &m.v, p.v, 3, dims, st, boxv, CU_TENSOR_MAP_SWIZZLE_128B);
  }
  {
    const cuuint64_t dims[3] = {16, 640, 40}, st[2] = {1280, 32};
    const cuuint32_t box[3] = {16, 40, 5};
    encode(fn, &m.wo, p.wo, 3, dims, st, box, CU_TENSOR_MAP_SWIZZLE_32B);
  }
  {
    const cuuint64_t dims[2] = {2048, 640}, st[1] = {Y_PITCH * 16};
    const cuuint32_t box[2] = {64, 80};
    encode(fn, &m.y, yaddr, 2, dims, st, box, CU_TENSOR_MAP_SWIZZLE_128B);
    const cuuint64_t stu[1] = {U_PITCH * 16};
    const cuuint32_t boxu[2] = {32, 64};
    encode(fn, &m.u, uaddr, 2, dims, stu, boxu, CU_TENSOR_MAP_SWIZZLE_NONE);
  }
  {
    const cuuint64_t dims[2] = {640, 2048}, st[1] = {1280};
    const cuuint32_t bqm[2] = {QBOX ? 80 : 64, 128}, bqt[2] = {16, 128}, bom[2] = {QBOX ? 80 : 64, 16}, bot[2] = {16, 16};
    encode(fn, &m.qm, p.q, 2, dims, st, bqm, QBOX ? CU_TENSOR_MAP_SWIZZLE_NONE : CU_TENSOR_MAP_SWIZZLE_128B);
    encode(fn, &m.qt, p.q, 2, dims, st, bqt, CU_TENSOR_MAP_SWIZZLE_32B);
    encode(fn, &m.om, p.out, 2, dims, st, bom, QBOX ? CU_TENSOR_MAP_SWIZZLE_NONE : CU_TENSOR_MAP_SWIZZLE_128B);
    encode(fn, &m.ot, p.out, 2, dims, st, bot, CU_TENSOR_MAP_SWIZZLE_32B);
  }
  fused_kernel<<<NCTA, NTHR, SMEM_BYTES>>>(m, p);
}
```

```cpp
#include <cuda.h>
#include <cuda_bf16.h>
#include <cuda_runtime.h>
#include <stdint.h>

namespace {

constexpr int SEQ = 2048, DIM = 640, NCTA = 128, NTHR = 512;

#define TRIG_KB 9
#define KV_KB 2
#define DEV_EXIT 0
#define ATT_GATE 0
#define G_AFTER 0
#define FENCE_LO 0
#define FENCE_HI 0
#define PW2 1
#define ENDBAR 0
#define PAD_KB 0
#define Y_ALIAS 1
#define NOMB 0
#define SRC_ROT 0
#define WAIT_NS 0
#define WB_TRIG B_USIG
#define G_POS 0
#define TAILF 1
#define T_ISSUE 384
#define T_PF 416
#define T_INIT 448
#define ATT_MERGE 0
#define BMAP 1
#define KV_MIX 0
#define O_DEFER 0
#define TASK0 0x3
#define TASK1 0x52
#define TASK2 0x41
#define HALO_FIRST 1
#define PREV_EARLY 0
#define Y_RB 2
#define O_RB 2
#define O_EAGER 1
#define OP_TRIG B_ATTN
#define FUSE_MIX 1
#define Q_EARLY 1
#define U_TRIM 1
#define Q_SLOT 3
#define G_TMA 1
#define W_RB 1
#define WPF B_S3
#define WPF_LIN 1
#define QBOX 0
#define FAST0 1
#define ACQ 0
#define U_TMA 0
#define U_GATE 0
#define RF_GATE 0
#define WO_TRIG B_WST
#define WL_TRIG B_WOP
#define WO_GATE 4

constexpr uint32_t STAGE_BYTES = 47104, ST_W = 16384, ST_WT = 40960;
constexpr uint32_t O_BYTES = 20480, WO_BYTES = 12800;
constexpr uint32_t OFF_OA = 0;
constexpr uint32_t OFF_QS = Q_SLOT * O_BYTES, OFF_QT = OFF_QS + 16384;
constexpr uint32_t OFF_WC = 81920;
constexpr uint32_t OFF_WA = 94720;
constexpr uint32_t OFF_GATE = 145920;
constexpr uint32_t OFF_TT = 146432;
constexpr uint32_t OFF_KVX = 148480;
constexpr uint32_t OFF_CH3 = 163840;
constexpr uint32_t CH_BYTES = 12288, U_BYTES = 4096;
constexpr uint32_t OFF_FT = 225280, OFF_GT = 229376;
constexpr uint32_t OFF_CH0 = 188416;
constexpr uint32_t OFF_KVS = OFF_CH0, KVS_V = 4480, KVS_BYTES = 8576;
constexpr uint32_t OFF_WS = OFF_WA;
__device__ __forceinline__ uint32_t off_us(int s) { return OFF_CH0 + 4096 * ((0x65320 >> (4 * s)) & 7); }
constexpr uint32_t OFF_YT = 163840;
constexpr uint32_t OFF_BAR = 231936;
constexpr uint32_t SMEM_BYTES = OFF_BAR + 512;

enum : uint32_t {
  B_FULL1 = 0, B_EMPTY1 = 4, B_S3 = 7, B_FULL2 = 52, B_EMPTY2 = 13, B_U = 8, B_GATE = 12, B_HA = 19, B_HB = 20,
  B_ATTN = 21, B_C34 = 22, B_YRB = 23, B_YFULL = 24, B_EPOCH = 25, B_PREP = 26, B_P1 = 27, B_LAST = 28,
  B_E3 = 29, B_OSIG = 30, B_WOP = 31, B_USIG = 32, B_WST = 33, B_KV = 34, B_KVD = 39, B_QF = 17, B_ATT2 = 18, B_YST = 40,
  B_ORB = 45, B_F0 = 33 + 15, B_CVD = 33 + 14, B_US = 45, B_YSIG = 50
};
constexpr uint32_t OFF_EPOCH = OFF_BAR + 8 * 51, OFF_D = OFF_BAR + 8 * 60;
__device__ __forceinline__ uint32_t off_o(int j) { return j < 4 ? OFF_OA + j * O_BYTES : j < 6 ? OFF_CH0 + (j - 4) * O_BYTES : OFF_OA + (j - 6) * O_BYTES; }
__device__ __forceinline__ uint32_t off_w(int j) { return j < 4 ? OFF_WA + j * WO_BYTES : j == 4 ? OFF_KVX : j == 5 ? OFF_WC : OFF_WA + (j - 6) * WO_BYTES; }
__device__ __forceinline__ int step_src(int hg, int j) {
  if (SRC_ROT == 2) {
    const int pos = (0x37621540 >> (4 * hg)) & 7;
    return j == 0 ? hg : (0x65217430 >> (4 * (j <= pos ? j - 1 : j))) & 7;
  }
  return SRC_ROT ? (hg + j) & 7 : j == 0 ? hg : j <= hg ? j - 1 : j;
}
__device__ __forceinline__ bool tail_first(int hg) { return TAILF && (hg & 3) == 3; }
__device__ __forceinline__ uint32_t off_ch(int c) { return (c < 3 ? OFF_CH0 : OFF_CH3 - 3 * CH_BYTES) + c * CH_BYTES; }

#define U_PITCH 264
__device__ __align__(1024) uint4 g_U[DIM * U_PITCH];
__device__ uint4 g_O[NCTA * 1280];
#define g_Y g_U
constexpr int Y_PITCH = U_PITCH;
__device__ uint4 g_WO[64 * 800];
__device__ uint4 g_halo[NCTA * 2 * 7 * 32];
__device__ __align__(128) float g_gate[SEQ + PAD_KB * 256];
__device__ unsigned g_cnt[32 * (1 + 2 * 16 + 8 + NCTA)];
constexpr int C_LAUNCH = 0, C_PREP = 32, C_Y = 32 * 17, C_W = 32 * 33, C_O = 32 * 41;

#define TSM(cond, slot) do { } while (0)
#define TSIF(cond, slot) do { if (__LINE__ >= FENCE_LO && __LINE__ < FENCE_HI) sched_fence(); } while (0)
__device__ __forceinline__ void sched_fence() {
  asm volatile("{\n.reg .pred p;\n.reg .u32 c;\nmov.u32 c, %%clock;\nsetp.eq.u32 p, c, 0;\n@p st.shared.u32 [%0], c;\n}"
               ::"r"(1024 + OFF_EPOCH + 4) : "memory");
}
#define TS(slot) TSIF(true, slot)

struct Params {
  const __nv_bfloat16 *q, *k, *v, *shift_k, *ssm_k, *ssm_D, *wqkv, *wo, *gate_w;
  __nv_bfloat16* out;
  uint32_t zero;
};

#define POLL_NS 0
constexpr int SPIN_LIMIT = 1 << 17;

__device__ __forceinline__ void mbar_init(uint32_t bar, uint32_t count) {
  asm volatile("mbarrier.init.shared::cta.b64 [%0], %1;" ::"r"(bar), "r"(count) : "memory");
}
__device__ __forceinline__ void mbar_expect_tx(uint32_t bar, uint32_t bytes) {
  asm volatile("mbarrier.arrive.expect_tx.shared::cta.b64 _, [%0], %1;" ::"r"(bar), "r"(bytes) : "memory");
}
__device__ __forceinline__ void mbar_arrive(uint32_t bar) {
  asm volatile("mbarrier.arrive.shared::cta.b64 _, [%0];" ::"r"(bar) : "memory");
}
__device__ __forceinline__ void mbar_wait(uint32_t bar, uint32_t parity) {
  uint32_t ok;
  int spins = 0;
  do {
    if (WAIT_NS)
      asm volatile("{\n.reg .pred p;\nmbarrier.try_wait.parity.shared::cta.b64 p, [%1], %2, %3;\nselp.b32 %0, 1, 0, p;\n}"
                   : "=r"(ok) : "r"(bar), "r"(parity), "r"(WAIT_NS) : "memory");
    else
      asm volatile("{\n.reg .pred p;\nmbarrier.try_wait.parity.shared::cta.b64 p, [%1], %2;\nselp.b32 %0, 1, 0, p;\n}"
                   : "=r"(ok) : "r"(bar), "r"(parity) : "memory");
    if (++spins > SPIN_LIMIT) break;
  } while (!ok);
}
__device__ __forceinline__ unsigned flag_read(const unsigned* p) {
  unsigned v;
  asm volatile("ld.relaxed.gpu.global.u32 %0, [%1];" : "=r"(v) : "l"(p) : "memory");
  return v;
}
__device__ __forceinline__ void flag_poll(const unsigned* p, unsigned target) {
  unsigned v;
  int spins = 0;
  do {
    if (POLL_NS && spins) __nanosleep(POLL_NS);
    asm volatile("ld.relaxed.gpu.global.u32 %0, [%1];" : "=r"(v) : "l"(p) : "memory");
    if (++spins > SPIN_LIMIT) break;
  } while ((int)(v - target) < 0);
}
__device__ __forceinline__ void flag_wait(const unsigned* p, unsigned target) {
  flag_poll(p, target);
  if (ACQ) asm volatile("fence.acquire.gpu;\nfence.proxy.async.global;" ::: "memory");
}
__device__ __forceinline__ void flag_signal(unsigned* p, int n, int lane) {
  if (lane == 0) asm volatile("fence.release.gpu;" ::: "memory");
  __syncwarp();
  if (lane < n) asm volatile("red.relaxed.gpu.global.add.u32 [%0], 1;" ::"l"(p + 32 * lane) : "memory");
}
__device__ __forceinline__ void flag_bump(unsigned* p) {
  asm volatile("red.relaxed.gpu.global.add.u32 [%0], 1;" ::"l"(p) : "memory");
}
__device__ __forceinline__ void fence_async_smem() { asm volatile("fence.proxy.async.shared::cta;" ::: "memory"); }
__device__ __forceinline__ void wg_sync(int id) { asm volatile("bar.sync %0, 128;" ::"r"(id) : "memory"); }

__device__ __forceinline__ void tma_2d(uint32_t dst, const CUtensorMap* tm, int c0, int c1, uint32_t bar) {
  asm volatile("cp.async.bulk.tensor.2d.shared::cluster.global.mbarrier::complete_tx::bytes [%0], [%1, {%3, %4}], [%2];"
               ::"r"(dst), "l"(tm), "r"(bar), "r"(c0), "r"(c1) : "memory");
}
__device__ __forceinline__ void tma_3d(uint32_t dst, const CUtensorMap* tm, int c0, int c1, int c2, uint32_t bar) {
  asm volatile("cp.async.bulk.tensor.3d.shared::cluster.global.mbarrier::complete_tx::bytes [%0], [%1, {%3, %4, %5}], [%2];"
               ::"r"(dst), "l"(tm), "r"(bar), "r"(c0), "r"(c1), "r"(c2) : "memory");
}
__device__ __forceinline__ void bulk_load(uint32_t dst, const void* src, uint32_t bytes, uint32_t bar) {
  asm volatile("cp.async.bulk.shared::cluster.global.mbarrier::complete_tx::bytes [%0], [%1], %2, [%3];"
               ::"r"(dst), "l"(src), "r"(bytes), "r"(bar) : "memory");
}
__device__ __forceinline__ void tm_prefetch(const CUtensorMap* tm) {
  asm volatile("prefetch.tensormap [%0];" ::"l"(tm) : "memory");
}

__device__ __forceinline__ void wg_fence() { asm volatile("wgmma.fence.sync.aligned;" ::: "memory"); }
__device__ __forceinline__ void wg_commit() { asm volatile("wgmma.commit_group.sync.aligned;" ::: "memory"); }
template <int N> __device__ __forceinline__ void wg_wait() { asm volatile("wgmma.wait_group.sync.aligned %0;" ::"n"(N) : "memory"); }
__device__ __forceinline__ uint32_t desc_lo(uint32_t addr, uint32_t lbo) { return ((addr & 0x3FFFF) >> 4) | ((lbo >> 4) << 16); }
constexpr uint32_t desc_hi(uint32_t sbo, uint32_t swz) { return (sbo >> 4) | (swz << 30); }
constexpr uint32_t HI_SW128 = desc_hi(1024, 1), HI_SW64 = desc_hi(512, 2), HI_SW32 = desc_hi(256, 3), HI_NONE = desc_hi(128, 0);
template <int N> __device__ __forceinline__ void pin(float* d) {
#pragma unroll
  for (int i = 0; i < N; i++) asm volatile("" : "+f"(d[i])::"memory");
}

__device__ __forceinline__ uint32_t lds32(uint32_t a) {
  uint32_t v;
  asm volatile("ld.volatile.shared.u32 %0, [%1];" : "=r"(v) : "r"(a) : "memory");
  return v;
}
__device__ __forceinline__ uint4 ldg128(const void* a) {
  uint4 v;
  asm volatile("ld.global.nc.v4.u32 {%0, %1, %2, %3}, [%4];" : "=r"(v.x), "=r"(v.y), "=r"(v.z), "=r"(v.w) : "l"(a) : "memory");
  return v;
}
__device__ __forceinline__ uint2 ldg64(const void* a) {
  uint2 v;
  asm volatile("ld.global.nc.v2.u32 {%0, %1}, [%2];" : "=r"(v.x), "=r"(v.y) : "l"(a) : "memory");
  return v;
}
__device__ __forceinline__ void ldsm4(uint32_t* r, uint32_t a) {
  asm volatile("ldmatrix.sync.aligned.m8n8.x4.shared.b16 {%0, %1, %2, %3}, [%4];"
               : "=r"(r[0]), "=r"(r[1]), "=r"(r[2]), "=r"(r[3]) : "r"(a) : "memory");
}
__device__ __forceinline__ void ldsm4t(uint32_t* r, uint32_t a) {
  asm volatile("ldmatrix.sync.aligned.m8n8.x4.trans.shared.b16 {%0, %1, %2, %3}, [%4];"
               : "=r"(r[0]), "=r"(r[1]), "=r"(r[2]), "=r"(r[3]) : "r"(a) : "memory");
}
__device__ __forceinline__ uint2 lds64(uint32_t a) {
  uint2 v;
  asm volatile("ld.shared.v2.u32 {%0, %1}, [%2];" : "=r"(v.x), "=r"(v.y) : "r"(a) : "memory");
  return v;
}
__device__ __forceinline__ uint4 lds128(uint32_t a) {
  uint4 v;
  asm volatile("ld.shared.v4.u32 {%0, %1, %2, %3}, [%4];" : "=r"(v.x), "=r"(v.y), "=r"(v.z), "=r"(v.w) : "r"(a) : "memory");
  return v;
}
__device__ __forceinline__ void sts128(uint32_t a, uint32_t x, uint32_t y, uint32_t z, uint32_t w) {
  asm volatile("st.shared.v4.u32 [%0], {%1, %2, %3, %4};" ::"r"(a), "r"(x), "r"(y), "r"(z), "r"(w) : "memory");
}
__device__ __forceinline__ void stsm4(uint32_t a, const uint32_t* r) {
  asm volatile("stmatrix.sync.aligned.m8n8.x4.shared.b16 [%0], {%1, %2, %3, %4};" ::"r"(a), "r"(r[0]), "r"(r[1]), "r"(r[2]), "r"(r[3]) : "memory");
}
__device__ __forceinline__ void stsm4t(uint32_t a, const uint32_t* r) {
  asm volatile("stmatrix.sync.aligned.m8n8.x4.trans.shared.b16 [%0], {%1, %2, %3, %4};" ::"r"(a), "r"(r[0]), "r"(r[1]), "r"(r[2]), "r"(r[3]) : "memory");
}
__device__ __forceinline__ uint32_t pack2(float lo, float hi) {
  uint32_t r;
  asm("cvt.rn.bf16x2.f32 %0, %1, %2;" : "=r"(r) : "f"(hi), "f"(lo));
  return r;
}
__device__ __forceinline__ uint32_t movm(uint32_t a) {
  uint32_t d;
  asm volatile("movmatrix.sync.aligned.m8n8.trans.b16 %0, %1;" : "=r"(d) : "r"(a));
  return d;
}
__device__ __forceinline__ uint32_t bmul(uint32_t a, uint32_t b) {
  uint32_t d;
  asm("mul.rn.bf16x2 %0, %1, %2;" : "=r"(d) : "r"(a), "r"(b));
  return d;
}
__device__ __forceinline__ uint32_t badd(uint32_t a, uint32_t b) {
  uint32_t d;
  asm("add.rn.bf16x2 %0, %1, %2;" : "=r"(d) : "r"(a), "r"(b));
  return d;
}
__device__ __forceinline__ uint32_t bfma(uint32_t a, uint32_t b, uint32_t c) {
  uint32_t d;
  asm("fma.rn.bf16x2 %0, %1, %2, %3;" : "=r"(d) : "r"(a), "r"(b), "r"(c));
  return d;
}
__device__ __forceinline__ float bf_lo(uint32_t x) { return __uint_as_float(x << 16); }
__device__ __forceinline__ float bf_hi(uint32_t x) { return __uint_as_float(x & 0xFFFF0000u); }
__device__ __forceinline__ float ex2(float x) {
  float y;
  asm("ex2.approx.ftz.f32 %0, %1;" : "=f"(y) : "f"(x));
  return y;
}
__device__ __forceinline__ float rcp(float x) {
  float y;
  asm("rcp.approx.ftz.f32 %0, %1;" : "=f"(y) : "f"(x));
  return y;
}
__device__ __forceinline__ void mma16816(float* d, uint32_t a0, uint32_t a1, uint32_t a2, uint32_t a3, uint32_t b0, uint32_t b1) {
  asm volatile("mma.sync.aligned.m16n8k16.row.col.f32.bf16.bf16.f32 {%0, %1, %2, %3}, {%4, %5, %6, %7}, {%8, %9}, {%0, %1, %2, %3};"
               : "+f"(d[0]), "+f"(d[1]), "+f"(d[2]), "+f"(d[3])
               : "r"(a0), "r"(a1), "r"(a2), "r"(a3), "r"(b0), "r"(b1));
}
__device__ __forceinline__ void mma1688(float* d, uint32_t a0, uint32_t a1, uint32_t b0) {
  asm volatile("mma.sync.aligned.m16n8k8.row.col.f32.bf16.bf16.f32 {%0, %1, %2, %3}, {%4, %5}, {%6}, {%0, %1, %2, %3};"
               : "+f"(d[0]), "+f"(d[1]), "+f"(d[2]), "+f"(d[3])
               : "r"(a0), "r"(a1), "r"(b0));
}

template <int N> struct WgRS;
template <int N> struct WgSST;
template <> struct WgRS<32> {
  template <uint32_t HB>
  static __device__ __forceinline__ void mma(float* d, const uint32_t* a, uint32_t db) {
    asm volatile("{\n.reg .pred p;\n.reg .b64 db;\nsetp.ne.b32 p, %22, 0;\n"
      "mov.b64 db, {%20, %21};\n"
      "wgmma.mma_async.sync.aligned.m64n32k16.f32.bf16.bf16 {"
      "%0, %1, %2, %3, %4, %5, %6, %7, %8, %9, %10, %11, %12, %13, %14, %15"
      "}, {%16, %17, %18, %19}, db, p, 1, 1, 1;\n}\n"
      : "+f"(d[0]), "+f"(d[1]), "+f"(d[2]), "+f"(d[3]), "+f"(d[4]), "+f"(d[5]), "+f"(d[6]), "+f"(d[7]),
        "+f"(d[8]), "+f"(d[9]), "+f"(d[10]), "+f"(d[11]), "+f"(d[12]), "+f"(d[13]), "+f"(d[14]), "+f"(d[15])
      : "r"(a[0]), "r"(a[1]), "r"(a[2]), "r"(a[3]), "r"(db), "n"(HB), "n"(1));
  }
  template <uint32_t HB>
  static __device__ __forceinline__ void set(float* d, const uint32_t* a, uint32_t db) {
    asm volatile("{\n.reg .pred p;\n.reg .b64 db;\nsetp.ne.b32 p, %22, 0;\n"
      "mov.b64 db, {%20, %21};\n"
      "wgmma.mma_async.sync.aligned.m64n32k16.f32.bf16.bf16 {"
      "%0, %1, %2, %3, %4, %5, %6, %7, %8, %9, %10, %11, %12, %13, %14, %15"
      "}, {%16, %17, %18, %19}, db, p, 1, 1, 1;\n}\n"
      : "=f"(d[0]), "=f"(d[1]), "=f"(d[2]), "=f"(d[3]), "=f"(d[4]), "=f"(d[5]), "=f"(d[6]), "=f"(d[7]),
        "=f"(d[8]), "=f"(d[9]), "=f"(d[10]), "=f"(d[11]), "=f"(d[12]), "=f"(d[13]), "=f"(d[14]), "=f"(d[15])
      : "r"(a[0]), "r"(a[1]), "r"(a[2]), "r"(a[3]), "r"(db), "n"(HB), "n"(0));
  }
};
template <> struct WgRS<64> {
  template <uint32_t HB>
  static __device__ __forceinline__ void mma(float* d, const uint32_t* a, uint32_t db) {
    asm volatile("{\n.reg .pred p;\n.reg .b64 db;\nsetp.ne.b32 p, %38, 0;\n"
      "mov.b64 db, {%36, %37};\n"
      "wgmma.mma_async.sync.aligned.m64n64k16.f32.bf16.bf16 {"
      "%0, %1, %2, %3, %4, %5, %6, %7, %8, %9, %10, %11, %12, %13, %14, %15, "
      "%16, %17, %18, %19, %20, %21, %22, %23, %24, %25, %26, %27, %28, %29, %30, %31"
      "}, {%32, %33, %34, %35}, db, p, 1, 1, 1;\n}\n"
      : "+f"(d[0]), "+f"(d[1]), "+f"(d[2]), "+f"(d[3]), "+f"(d[4]), "+f"(d[5]), "+f"(d[6]), "+f"(d[7]),
        "+f"(d[8]), "+f"(d[9]), "+f"(d[10]), "+f"(d[11]), "+f"(d[12]), "+f"(d[13]), "+f"(d[14]), "+f"(d[15]),
        "+f"(d[16]), "+f"(d[17]), "+f"(d[18]), "+f"(d[19]), "+f"(d[20]), "+f"(d[21]), "+f"(d[22]), "+f"(d[23]),
        "+f"(d[24]), "+f"(d[25]), "+f"(d[26]), "+f"(d[27]), "+f"(d[28]), "+f"(d[29]), "+f"(d[30]), "+f"(d[31])
      : "r"(a[0]), "r"(a[1]), "r"(a[2]), "r"(a[3]), "r"(db), "n"(HB), "n"(1));
  }
  template <uint32_t HB>
  static __device__ __forceinline__ void set(float* d, const uint32_t* a, uint32_t db) {
    asm volatile("{\n.reg .pred p;\n.reg .b64 db;\nsetp.ne.b32 p, %38, 0;\n"
      "mov.b64 db, {%36, %37};\n"
      "wgmma.mma_async.sync.aligned.m64n64k16.f32.bf16.bf16 {"
      "%0, %1, %2, %3, %4, %5, %6, %7, %8, %9, %10, %11, %12, %13, %14, %15, "
      "%16, %17, %18, %19, %20, %21, %22, %23, %24, %25, %26, %27, %28, %29, %30, %31"
      "}, {%32, %33, %34, %35}, db, p, 1, 1, 1;\n}\n"
      : "=f"(d[0]), "=f"(d[1]), "=f"(d[2]), "=f"(d[3]), "=f"(d[4]), "=f"(d[5]), "=f"(d[6]), "=f"(d[7]),
        "=f"(d[8]), "=f"(d[9]), "=f"(d[10]), "=f"(d[11]), "=f"(d[12]), "=f"(d[13]), "=f"(d[14]), "=f"(d[15]),
        "=f"(d[16]), "=f"(d[17]), "=f"(d[18]), "=f"(d[19]), "=f"(d[20]), "=f"(d[21]), "=f"(d[22]), "=f"(d[23]),
        "=f"(d[24]), "=f"(d[25]), "=f"(d[26]), "=f"(d[27]), "=f"(d[28]), "=f"(d[29]), "=f"(d[30]), "=f"(d[31])
      : "r"(a[0]), "r"(a[1]), "r"(a[2]), "r"(a[3]), "r"(db), "n"(HB), "n"(0));
  }
};
template <> struct WgSST<48> {
  template <uint32_t HA, uint32_t HB>
  static __device__ __forceinline__ void mma(float* d, uint32_t da, uint32_t db, int sc) {
    asm volatile("{\n.reg .pred p;\n.reg .b64 da, db;\nsetp.ne.b32 p, %28, 0;\n"
      "mov.b64 da, {%24, %25};\nmov.b64 db, {%26, %27};\n"
      "wgmma.mma_async.sync.aligned.m64n48k16.f32.bf16.bf16 {"
      "%0, %1, %2, %3, %4, %5, %6, %7, %8, %9, %10, %11, %12, %13, %14, %15, "
      "%16, %17, %18, %19, %20, %21, %22, %23"
      "}, da, db, p, 1, 1, 0, 1;\n}\n"
      : "+f"(d[0]), "+f"(d[1]), "+f"(d[2]), "+f"(d[3]), "+f"(d[4]), "+f"(d[5]), "+f"(d[6]), "+f"(d[7]),
        "+f"(d[8]), "+f"(d[9]), "+f"(d[10]), "+f"(d[11]), "+f"(d[12]), "+f"(d[13]), "+f"(d[14]), "+f"(d[15]),
        "+f"(d[16]), "+f"(d[17]), "+f"(d[18]), "+f"(d[19]), "+f"(d[20]), "+f"(d[21]), "+f"(d[22]), "+f"(d[23])
      : "r"(da), "n"(HA), "r"(db), "n"(HB), "r"(sc));
  }
};
template <> struct WgSST<80> {
  template <uint32_t HA, uint32_t HB>
  static __device__ __forceinline__ void mma(float* d, uint32_t da, uint32_t db, int sc) {
    asm volatile("{\n.reg .pred p;\n.reg .b64 da, db;\nsetp.ne.b32 p, %44, 0;\n"
      "mov.b64 da, {%40, %41};\nmov.b64 db, {%42, %43};\n"
      "wgmma.mma_async.sync.aligned.m64n80k16.f32.bf16.bf16 {"
      "%0, %1, %2, %3, %4, %5, %6, %7, %8, %9, %10, %11, %12, %13, %14, %15, "
      "%16, %17, %18, %19, %20, %21, %22, %23, %24, %25, %26, %27, %28, %29, %30, %31, "
      "%32, %33, %34, %35, %36, %37, %38, %39"
      "}, da, db, p, 1, 1, 0, 1;\n}\n"
      : "+f"(d[0]), "+f"(d[1]), "+f"(d[2]), "+f"(d[3]), "+f"(d[4]), "+f"(d[5]), "+f"(d[6]), "+f"(d[7]),
        "+f"(d[8]), "+f"(d[9]), "+f"(d[10]), "+f"(d[11]), "+f"(d[12]), "+f"(d[13]), "+f"(d[14]), "+f"(d[15]),
        "+f"(d[16]), "+f"(d[17]), "+f"(d[18]), "+f"(d[19]), "+f"(d[20]), "+f"(d[21]), "+f"(d[22]), "+f"(d[23]),
        "+f"(d[24]), "+f"(d[25]), "+f"(d[26]), "+f"(d[27]), "+f"(d[28]), "+f"(d[29]), "+f"(d[30]), "+f"(d[31]),
        "+f"(d[32]), "+f"(d[33]), "+f"(d[34]), "+f"(d[35]), "+f"(d[36]), "+f"(d[37]), "+f"(d[38]), "+f"(d[39])
      : "r"(da), "n"(HA), "r"(db), "n"(HB), "r"(sc));
  }
};
template <> struct WgSST<192> {
  template <uint32_t HA, uint32_t HB>
  static __device__ __forceinline__ void mma(float* d, uint32_t da, uint32_t db, int sc) {
    asm volatile("{\n.reg .pred p;\n.reg .b64 da, db;\nsetp.ne.b32 p, %100, 0;\n"
      "mov.b64 da, {%96, %97};\nmov.b64 db, {%98, %99};\n"
      "wgmma.mma_async.sync.aligned.m64n192k16.f32.bf16.bf16 {"
      "%0, %1, %2, %3, %4, %5, %6, %7, %8, %9, %10, %11, %12, %13, %14, %15, "
      "%16, %17, %18, %19, %20, %21, %22, %23, %24, %25, %26, %27, %28, %29, %30, %31, "
      "%32, %33, %34, %35, %36, %37, %38, %39, %40, %41, %42, %43, %44, %45, %46, %47, "
      "%48, %49, %50, %51, %52, %53, %54, %55, %56, %57, %58, %59, %60, %61, %62, %63, "
      "%64, %65, %66, %67, %68, %69, %70, %71, %72, %73, %74, %75, %76, %77, %78, %79, "
      "%80, %81, %82, %83, %84, %85, %86, %87, %88, %89, %90, %91, %92, %93, %94, %95"
      "}, da, db, p, 1, 1, 0, 1;\n}\n"
      : "+f"(d[0]), "+f"(d[1]), "+f"(d[2]), "+f"(d[3]), "+f"(d[4]), "+f"(d[5]), "+f"(d[6]), "+f"(d[7]),
        "+f"(d[8]), "+f"(d[9]), "+f"(d[10]), "+f"(d[11]), "+f"(d[12]), "+f"(d[13]), "+f"(d[14]), "+f"(d[15]),
        "+f"(d[16]), "+f"(d[17]), "+f"(d[18]), "+f"(d[19]), "+f"(d[20]), "+f"(d[21]), "+f"(d[22]), "+f"(d[23]),
        "+f"(d[24]), "+f"(d[25]), "+f"(d[26]), "+f"(d[27]), "+f"(d[28]), "+f"(d[29]), "+f"(d[30]), "+f"(d[31]),
        "+f"(d[32]), "+f"(d[33]), "+f"(d[34]), "+f"(d[35]), "+f"(d[36]), "+f"(d[37]), "+f"(d[38]), "+f"(d[39]),
        "+f"(d[40]), "+f"(d[41]), "+f"(d[42]), "+f"(d[43]), "+f"(d[44]), "+f"(d[45]), "+f"(d[46]), "+f"(d[47]),
        "+f"(d[48]), "+f"(d[49]), "+f"(d[50]), "+f"(d[51]), "+f"(d[52]), "+f"(d[53]), "+f"(d[54]), "+f"(d[55]),
        "+f"(d[56]), "+f"(d[57]), "+f"(d[58]), "+f"(d[59]), "+f"(d[60]), "+f"(d[61]), "+f"(d[62]), "+f"(d[63]),
        "+f"(d[64]), "+f"(d[65]), "+f"(d[66]), "+f"(d[67]), "+f"(d[68]), "+f"(d[69]), "+f"(d[70]), "+f"(d[71]),
        "+f"(d[72]), "+f"(d[73]), "+f"(d[74]), "+f"(d[75]), "+f"(d[76]), "+f"(d[77]), "+f"(d[78]), "+f"(d[79]),
        "+f"(d[80]), "+f"(d[81]), "+f"(d[82]), "+f"(d[83]), "+f"(d[84]), "+f"(d[85]), "+f"(d[86]), "+f"(d[87]),
        "+f"(d[88]), "+f"(d[89]), "+f"(d[90]), "+f"(d[91]), "+f"(d[92]), "+f"(d[93]), "+f"(d[94]), "+f"(d[95])
      : "r"(da), "n"(HA), "r"(db), "n"(HB), "r"(sc));
  }
};

struct FftConst {
  uint32_t f[2][4], fi[4][4];
  uint32_t ta[2][2], tb[2][2];
};
__device__ __forceinline__ void cis(int m, float scale, float& c, float& s) {
  const float a = (float)m * (-6.283185307179586f * scale);
  c = __cosf(a);
  s = __sinf(a);
}
__device__ __forceinline__ void fft_tables(uint32_t (&v)[12], int tw) {
  const int row = tw >> 2, ch = tw & 3;
#pragma unroll
  for (int i = 0; i < 4; i++) {
    float c[2], s[2], x[2];
#pragma unroll
    for (int e = 0; e < 2; e++) {
      cis((((32 * (8 * ch + 2 * i + e) + 15) * (4 * row - 63) + 2048) & 4095) - 2048, 1.f / 4096, c[e], s[e]);
      float gc, gs;
      cis((((row & 15) * (8 * (ch & 1) + 2 * i + e) + 8) & 15) - 8, 1.f / 16, gc, gs);
      x[e] = (row >> 4) == (ch >> 1) ? gc : (ch >> 1) ? gs : -gs;
    }
    v[i] = pack2(c[0] * 0.125f, c[1] * 0.125f);
    v[4 + i] = pack2(s[0] * 0.125f, s[1] * 0.125f);
    v[8 + i] = pack2(x[0], x[1]);
  }
#pragma unroll
  for (int i = 0; i < 12; i++) asm volatile("" : "+r"(v[i]));
}
__device__ __forceinline__ void fft_tables_store(const uint32_t (&v)[12], uint32_t sb, int tw) {
  const int row = tw >> 2;
  const uint32_t x = ((tw ^ (row >> 1)) & 3) << 4, a = sb + OFF_FT + (16 * (row >> 3) + (row & 7)) * 64 + x;
  sts128(a, v[0], v[1], v[2], v[3]);
  sts128(a + 512, v[4], v[5], v[6], v[7]);
  sts128(sb + OFF_GT + row * 64 + x, v[8], v[9], v[10], v[11]);
}
__device__ __forceinline__ void fft_twiddles(uint32_t (&v)[2], int tw) {
  float a[2], s[2];
#pragma unroll
  for (int i = 0; i < 2; i++) {
    float c;
    cis((2 * (2 * (tw & 3) + i) - 15) * (4 * (tw >> 2) - 63), 1.f / 4096, c, s[i]);
    a[i] = __fdividef(-s[i], 1.f + c);
  }
  v[0] = pack2(a[0], a[1]);
  v[1] = pack2(s[0], s[1]);
  asm volatile("" : "+r"(v[0]), "+r"(v[1]));
}
__device__ __forceinline__ void fft_matrices(FftConst& k, uint32_t sb, int w, int lane) {
  const uint32_t x = (lane >> 1) & 3;
  const uint2 t0 = lds64(sb + OFF_TT + 256 * w + 8 * lane), t1 = lds64(sb + OFF_TT + 256 * w + 8 * (lane ^ 3));
  k.ta[0][0] = t0.x;
  k.tb[0][0] = t0.y;
  k.ta[1][1] = __byte_perm(t1.x, 0, 0x1032);
  k.tb[1][1] = __byte_perm(t1.y, 0, 0x1032);
#pragma unroll
  for (int j = 0; j < 2; j++) {
    k.ta[1 - j][j] = k.ta[j][j] ^ 0x80008000u;
    k.tb[1 - j][j] = k.tb[j][j] ^ 0x80008000u;
    asm volatile("" : "+r"(k.ta[0][j]), "+r"(k.tb[0][j]), "+r"(k.ta[1][j]), "+r"(k.tb[1][j]));
  }
#pragma unroll
  for (int i = 0; i < 2; i++) {
    ldsm4(k.f[i], sb + OFF_FT + (16 * w + (lane & 15)) * 64 + (((2 * i + (lane >> 4)) ^ x) << 4));
    ldsm4t(k.fi[i], sb + OFF_FT + (32 * i + lane) * 64 + ((w ^ x) << 4));
#pragma unroll
    for (int j = 0; j < 4; j++) {
      k.fi[2 + i][j] = (j & 1) ? k.fi[i][j - 1] ^ 0x80008000u : k.fi[i][j + 1];
      asm volatile("" : "+r"(k.fi[2 + i][j]));
    }
  }
}
__device__ __forceinline__ void rot(uint32_t& x, uint32_t& y, uint32_t a, uint32_t b) {
  x = bfma(a, y, x);
  y = bfma(b, x, y);
  x = bfma(a, y, x);
}
__device__ __forceinline__ void twiddle_fwd(uint32_t (&a)[4][4], float* d, const FftConst& k) {
#pragma unroll
  for (int q = 0; q < 4; q++)
#pragma unroll
    for (int j = 0; j < 2; j++) {
      const float* x = d + 8 * q + 4 * j;
      uint32_t re = pack2(x[0], x[1]), im = pack2(x[2], x[3]);
      rot(re, im, k.ta[0][j], k.tb[0][j]);
      a[q & 2][2 * j + (q & 1)] = re;
      a[(q & 2) + 1][2 * j + (q & 1)] = im;
    }
}
__device__ __forceinline__ void g_step(float* d, const uint32_t (&a)[4][4], uint32_t dre, uint32_t dim) {
  WgRS<32>::set<HI_SW64>(d, a[0], dre);
  WgRS<32>::set<HI_SW64>(d + 16, a[2], dre);
  WgRS<32>::mma<HI_SW64>(d, a[1], dim);
  WgRS<32>::mma<HI_SW64>(d + 16, a[3], dim);
  wg_commit();
}

__device__ __forceinline__ void products(uint32_t (&a)[4][4], const float* H, const float* U, int p) {
#pragma unroll
  for (int j = 0; j < 2; j++)
#pragma unroll
    for (int m = 2 * p; m < 2 * p + 2; m++) {
      float pr[2], pi[2];
#pragma unroll
      for (int x = 0; x < 2; x++)
#pragma unroll
        for (int q = 0; q <= m; q++) {
          const int ih = 16 * (q >> 1) + 2 * (q & 1) + 4 * j + x, iu = 16 * ((m - q) >> 1) + 2 * ((m - q) & 1) + 4 * j + x;
          pr[x] = q ? fmaf(H[ih], U[iu], pr[x]) : H[ih] * U[iu];
          pi[x] = q ? fmaf(H[ih], U[iu + 8], pi[x]) : H[ih] * U[iu + 8];
          pr[x] = fmaf(-H[ih + 8], U[iu + 8], pr[x]);
          pi[x] = fmaf(H[ih + 8], U[iu], pi[x]);
        }
      a[m & 2][2 * j + (m & 1)] = pack2(pr[0], pr[1]);
      a[(m & 2) + 1][2 * j + (m & 1)] = pack2(pi[0], pi[1]);
    }
}

__device__ __forceinline__ void conv_channel(const FftConst& k, uint32_t sb, int c, int wg, int w, int lane) {
  const uint32_t cb = sb + off_ch(c), bars = sb + OFF_BAR;
  const uint32_t du = desc_lo(cb, 1024), dg = desc_lo(sb + OFF_GT, 16), dz = desc_lo(cb + U_BYTES, 16);
  float U[32], H[32];
  uint32_t a[4][4], e[4][4];
  const float dv = __uint_as_float(lds32(sb + OFF_D + 4 * c));
  wg_fence();
  WgRS<64>::set<HI_SW32>(H, k.f[0], du + 256);
  WgRS<64>::mma<HI_SW32>(H, k.f[1], du + 256 + 32);
  wg_commit();
  wg_wait<0>();
  pin<32>(H);
  twiddle_fwd(a, H, k);
  if (ATT_GATE) mbar_wait(bars + 8 * (ATT_GATE == 1 ? B_ATTN : B_ATT2), 0);
  mbar_wait(bars + 8 * (B_U + (c < 3 ? c : 3)), 0);
  TSM(w == 0 && c < 3, 7 + wg);
  wg_fence();
  WgRS<64>::set<HI_SW32>(U, k.f[0], du);
  WgRS<64>::mma<HI_SW32>(U, k.f[1], du + 32);
  wg_commit();
  g_step(H, a, dg, dg + 64);
  wg_wait<1>();
  pin<32>(U);
  twiddle_fwd(e, U, k);
  wg_fence();
  g_step(U, e, dg, dg + 64);
  wg_wait<0>();
  pin<32>(U);
  pin<32>(H);
#pragma unroll
  for (int j = 0; j < 4; j++) H[4 * (j >> 1) + (j & 1)] += dv;
  float V[32];
#pragma unroll
  for (int p = 0; p < 2; p++) {
    products(a, H, U, p);
    wg_fence();
    WgRS<32>::set<HI_SW64>(V + 16 * p, a[2 * p], dg + 64);
    WgRS<32>::mma<HI_SW64>(V + 16 * p, a[2 * p + 1], dg);
    wg_commit();
  }
  const uint32_t za = cb + U_BYTES + (8 * w + (lane & 7)) * 128 + (((lane >> 3) ^ (lane & 7)) << 4);
  const uint32_t ya = cb + (lane >> 4) * 1024 + (8 * w + (lane & 7)) * 32 + ((((lane >> 3) ^ (lane >> 2)) & 1) << 4);
  wg_sync(1 + wg);
#pragma unroll
  for (int p = 0; p < 2; p++) {
    if (p == 0) wg_wait<1>();
    else wg_wait<0>();
    pin<16>(V + 16 * p);
#pragma unroll
    for (int i = 0; i < 4; i++) {
      const int j = i & 1;
      const float* x = V + 16 * p + 4 * j + (i & 2);
      e[p][i] = pack2(x[8], x[9]);
      e[2 + p][i] = pack2(x[0], x[1]);
      rot(e[p][i], e[2 + p][i], k.ta[1][j], k.tb[1][j]);
    }
    stsm4(za ^ (64 * p), e[p]);
    stsm4((za ^ (64 * p)) + 4096, e[2 + p]);
  }
  fence_async_smem();
  wg_sync(1 + wg);
  wg_fence();
  WgRS<64>::set<HI_SW128>(H, k.fi[0], dz);
#pragma unroll
  for (int ks = 1; ks < 4; ks++) WgRS<64>::mma<HI_SW128>(H, k.fi[ks], dz + 128 * ks);
  wg_commit();
  if (WO_GATE == 3 && lane == 0) mbar_arrive(bars + 8 * B_CVD);
  wg_wait<0>();
  pin<32>(H);
  if (WO_GATE == 4 && lane == 0) mbar_arrive(bars + 8 * B_CVD);
  TSIF(w == 0, 88 + c);
#pragma unroll
  for (int j = 0; j < 8; j++)
    a[j >> 2][j & 3] = j < 2 ? pack2(H[4 * j], H[4 * j + 1]) : pack2(H[4 * j] + H[4 * j - 6], H[4 * j + 1] + H[4 * j - 5]);
  stsm4(ya, a[0]);
  stsm4(ya + 2048, a[1]);
  fence_async_smem();
  __syncwarp();
}

__device__ __forceinline__ void prep_slab(uint4* res, const uint2* sw, uint32_t sb, int slab, int w, int lane) {
  const int t = lane & 3, tp = (lane & 7) >> 1, pos = 8 * tp + 2 * (((lane >> 3) + tp) & 3) + (lane & 1);
  const uint32_t base = sb + OFF_KVS + slab * KVS_BYTES + pos * 128;
  uint32_t kk[2][4][4], vv[2][4];
  mbar_wait(sb + OFF_BAR + 8 * (B_KV + slab), 0);
#pragma unroll
  for (int h = 0; h < 2; h++) {
#pragma unroll
    for (int j = 0; j < 4; j++) {
      const uint32_t a = base + 128 * j;
      ldsm4t(kk[h][j], a + (((w + 4 * h) ^ ((a >> 7) & 7)) << 4));
    }
    const uint32_t a = base + KVS_V;
    ldsm4t(vv[h], a + (((w + 4 * h) ^ ((a >> 7) & 7)) << 4));
  }
#pragma unroll
  for (int h = 0; h < 2; h++) {
    uint32_t (&k)[4][4] = kk[h];
    uint32_t (&v)[4] = vv[h];
    const uint32_t w0 = __byte_perm(sw[h].x, 0, 0x1010), w1 = __byte_perm(sw[h].x, 0, 0x3232);
    const uint32_t w2 = __byte_perm(sw[h].y, 0, 0x1010), w3 = __byte_perm(sw[h].y, 0, 0x3232);
#pragma unroll
    for (int m = 0; m < 4; m++)
      v[m] = bmul(badd(badd(badd(bmul(k[0][m], w3), bmul(k[1][m], w2)), bmul(k[2][m], w1)), bmul(k[3][m], w0)), v[m]);
    uint32_t a[4];
#pragma unroll
    for (int m = 0; m < 4; m++) a[m] = (t & 1) ? v[(m + 3) & 3] : v[m];
    res[h] = (t & 2) ? make_uint4(a[2], a[3], a[0], a[1]) : make_uint4(a[0], a[1], a[2], a[3]);
  }
}

__device__ __forceinline__ void prep_gate(const Params& p, uint32_t sb, int b, int w, int lane) {
  uint2 gw[5], x[4][5];
#pragma unroll
  for (int j = 0; j < 5; j++) gw[j] = ldg64(reinterpret_cast<const uint2*>(p.gate_w) + lane + 32 * j);
#pragma unroll
  for (int i = 0; i < 4; i++)
#pragma unroll
    for (int j = 0; j < 5; j++)
      x[i][j] = ldg64(reinterpret_cast<const uint2*>(p.q) + (16 * b + 4 * w + i) * (DIM / 4) + lane + 32 * j);
  float s[4];
#pragma unroll
  for (int i = 0; i < 4; i++) {
    s[i] = 0.f;
#pragma unroll
    for (int j = 0; j < 5; j++) {
      const uint32_t m0 = bmul(x[i][j].x, gw[j].x), m1 = bmul(x[i][j].y, gw[j].y);
      s[i] += (bf_lo(m0) + bf_hi(m0)) + (bf_lo(m1) + bf_hi(m1));
    }
  }
  const bool h = lane & 16, q = lane & 8;
  const float a = (h ? s[2] : s[0]) + __shfl_xor_sync(0xffffffffu, h ? s[0] : s[2], 16);
  const float c = (h ? s[3] : s[1]) + __shfl_xor_sync(0xffffffffu, h ? s[1] : s[3], 16);
  float z = (q ? c : a) + __shfl_xor_sync(0xffffffffu, q ? a : c, 8);
#pragma unroll
  for (int o = 4; o > 0; o >>= 1) z += __shfl_xor_sync(0xffffffffu, z, o);
  z = bf_lo(pack2(z, 0.f));
  z = bf_lo(pack2(__fdividef(1.f, 1.f + __expf(-z)), 0.f));
  if (G_TMA) {
    mbar_wait(sb + OFF_BAR + 8 * B_S3, 0);
    if ((lane & 7) == 0) asm volatile("st.shared.f32 [%0], %1;" ::"r"(sb + OFF_GATE + 64 * (b & 7) + 16 * w + (lane >> 1)), "f"(z) : "memory");
    fence_async_smem();
  } else if ((lane & 7) == 0) {
    g_gate[16 * b + 4 * w + (lane >> 3)] = z;
  }
}

__device__ __forceinline__ uint32_t bmax(uint32_t a, uint32_t b) {
  uint32_t d;
  asm("max.bf16x2 %0, %1, %2;" : "=r"(d) : "r"(a), "r"(b));
  return d;
}
__device__ __forceinline__ void softmax_two(const float (&l)[2][2], uint32_t& p0, uint32_t& p1) {
  constexpr float kScale = 0.22360679774997896f, kLog2e = 1.4426950408889634f;
  const uint32_t r0 = pack2(l[0][0], l[1][0]), r1 = pack2(l[0][1], l[1][1]);
  const uint32_t x0 = pack2(bf_lo(r0) * kScale, bf_hi(r0) * kScale), x1 = pack2(bf_lo(r1) * kScale, bf_hi(r1) * kScale);
  uint32_t m = bmax(x0, x1);
  m = bmax(m, __shfl_xor_sync(0xffffffffu, m, 1));
  m = bmax(m, __shfl_xor_sync(0xffffffffu, m, 2));
  const float m0 = bf_lo(m) * kLog2e, m1 = bf_hi(m) * kLog2e;
  p0 = pack2(ex2(bf_lo(x0) * kLog2e - m0), ex2(bf_lo(x1) * kLog2e - m0));
  p1 = pack2(ex2(bf_hi(x0) * kLog2e - m1), ex2(bf_hi(x1) * kLog2e - m1));
}

__device__ __forceinline__ void halo_read(uint32_t (&kpv)[10], uint32_t (&vpv)[10], uint32_t (&tg)[7], const uint4* hp) {
#pragma unroll
  for (int j = 0; j < 7; j++) {
    uint32_t x0, x1, x2;
    asm volatile("ld.relaxed.gpu.global.v4.u32 {%0, %1, %2, %3}, [%4];"
                 : "=r"(x0), "=r"(x1), "=r"(x2), "=r"(tg[j]) : "l"(hp + 32 * j) : "memory");
    if (j < 4) kpv[3 * j] = x0; else vpv[3 * j - 10] = x0;
    if (j < 3) kpv[3 * j + 1] = x1; else vpv[3 * j - 9] = x1;
    if (j < 3) kpv[3 * j + 2] = x2; else if (j < 6) vpv[3 * j - 8] = x2;
  }
}

template <int ROT>
__device__ __forceinline__ void pack_qkv(const float* acc, uint32_t (&qlo)[10], uint32_t (&qhi)[10], uint32_t (&klo)[10],
                                         uint32_t (&khi)[10], uint32_t (&vlo)[10], uint32_t (&vhi)[10]) {
#pragma unroll
  for (int j = 0; j < 10; j++) {
    const int x = (j + ROT) % 10, tq = x < 8 ? x : 16 + x, tk = x < 8 ? 8 + x : 18 + x, tv = x < 8 ? 16 + x : 20 + x;
    khi[j] = pack2(acc[4 * tk + 2], acc[4 * tk + 3]);
    vhi[j] = movm(pack2(acc[4 * tv + 2], acc[4 * tv + 3]));
    qlo[j] = pack2(acc[4 * tq], acc[4 * tq + 1]);
    qhi[j] = pack2(acc[4 * tq + 2], acc[4 * tq + 3]);
    klo[j] = pack2(acc[4 * tk], acc[4 * tk + 1]);
    vlo[j] = pack2(acc[4 * tv], acc[4 * tv + 1]);
    asm volatile("" : "+r"(khi[j]), "+r"(qlo[j]), "+r"(qhi[j]), "+r"(klo[j]), "+r"(vlo[j]));
  }
}

template <int ROT> __device__ __forceinline__ void halo_send(const float* acc, uint4* ho, uint32_t tag) {
#pragma unroll
  for (int j = 0; j < 7; j++) {
    uint32_t x[3];
#pragma unroll
    for (int e = 0; e < 3; e++) {
      const int i = 3 * j + e, y = (i % 10 + ROT) % 10, tk = y < 8 ? 8 + y : 18 + y, tv = y < 8 ? 16 + y : 20 + y;
      x[e] = i < 10 ? pack2(acc[4 * tk + 2], acc[4 * tk + 3]) : i < 20 ? movm(pack2(acc[4 * tv + 2], acc[4 * tv + 3])) : 0u;
    }
    asm volatile("st.relaxed.gpu.global.v4.u32 [%0], {%1, %2, %3, %4};" ::"l"(ho + 32 * j), "r"(x[0]), "r"(x[1]), "r"(x[2]), "r"(tag) : "memory");
  }
}

__device__ __forceinline__ void attention(float* acc, uint32_t sb, int b, int par, int w, int lane, uint32_t tag, uint32_t zero) {
  const int g = lane >> 2, t = lane & 3;
  uint32_t klo[10], khi[10], vlo[10], vhi[10], qlo[10], qhi[10], kpv[10], vpv[10];
  if (HALO_FIRST && w == 3 && b < NCTA - 8) {
    uint4* ho = g_halo + (b * 2 + par) * 224 + lane;
    if (tail_first(b & 7)) halo_send<8>(acc, ho, tag);
    else halo_send<0>(acc, ho, tag);
    TSIF(par == 0, 76);
    pin<120>(acc);
  }
  if (tail_first(b & 7)) pack_qkv<8>(acc, qlo, qhi, klo, khi, vlo, vhi);
  else pack_qkv<0>(acc, qlo, qhi, klo, khi, vlo, vhi);
  const uint32_t xa = sb + OFF_KVX + (par * 3) * 2560 + lane * 16;
  if (w < 3) {
    sts128(xa + w * 2560, khi[0], khi[1], khi[2], khi[3]);
    sts128(xa + w * 2560 + 512, khi[4], khi[5], khi[6], khi[7]);
    sts128(xa + w * 2560 + 1024, khi[8], khi[9], vhi[0], vhi[1]);
    sts128(xa + w * 2560 + 1536, vhi[2], vhi[3], vhi[4], vhi[5]);
    sts128(xa + w * 2560 + 2048, vhi[6], vhi[7], vhi[8], vhi[9]);
  } else if (!HALO_FIRST && b < NCTA - 8) {
    uint4* ho = g_halo + (b * 2 + par) * 224 + lane;
#pragma unroll
    for (int j = 0; j < 7; j++) {
      const uint32_t x0 = j < 4 ? khi[3 * j] : vhi[3 * j - 10], x1 = j < 3 ? khi[3 * j + 1] : vhi[3 * j - 9];
      const uint32_t x2 = j < 3 ? khi[3 * j + 2] : j < 6 ? vhi[3 * j - 8] : 0u;
      asm volatile("st.relaxed.gpu.global.v4.u32 [%0], {%1, %2, %3, %4};" ::"l"(ho + 32 * j), "r"(x0), "r"(x1), "r"(x2), "r"(tag) : "memory");
    }
  }
  TSIF(par == 0 && w == 1, 64);
  TSIF(par == 0 && w == 3 && !HALO_FIRST, 76);
#pragma unroll
  for (int j = 0; j < 10; j++) vlo[j] = movm(vlo[j]);
  const bool far0 = 2 * t > g, far1 = 2 * t + 1 > g;
  const uint32_t mfar = (far0 ? 0x0000FFFFu : 0u) | (far1 ? 0xFFFF0000u : 0u);
  float slo[4][2], shi[4][2], lg[2][2];
  uint32_t phi[4], plo[4], qml[4], qmh[4];
#pragma unroll
  for (int h = 0; h < 4; h++) {
    const int f = h == 0 ? 0 : h == 1 ? 3 : h == 2 ? 5 : 8, hf = h < 2 ? 2 : 7;
    const bool mine = (h & 1) ? t >= 2 : t < 2;
    qml[h] = mine ? qlo[hf] : 0u;
    qmh[h] = mine ? qhi[hf] : 0u;
    float a[4] = {0.f, 0.f, 0.f, 0.f}, c[4] = {0.f, 0.f, 0.f, 0.f};
    mma16816(a, qlo[f], qhi[f], qlo[f + 1], qhi[f + 1], klo[f], klo[f + 1]);
    mma16816(c, qlo[f], qhi[f], qlo[f + 1], qhi[f + 1], khi[f], khi[f + 1]);
    mma1688(a, qml[h], qmh[h], klo[hf]);
    mma1688(c, qml[h], qmh[h], khi[hf]);
    slo[h][0] = a[0];
    slo[h][1] = a[1];
    shi[h][0] = lg[h & 1][0] = far0 ? a[2] : c[2];
    shi[h][1] = lg[h & 1][1] = far1 ? a[3] : c[3];
    if (!ATT_MERGE && (h & 1)) softmax_two(lg, phi[h - 1], phi[h]);
  }
  TSIF(par == 0 && w == 1, 65);
  if (ATT_GATE == 3 && lane == 0) mbar_arrive(sb + OFF_BAR + 8 * B_ATT2 + (phi[3] & zero));
  wg_sync(1 + par);
  TSIF(par == 0 && w == 1, 66);
  const bool nohist = (w == 0) && (b < 8);
  const uint4* hp = g_halo + ((b - 8) * 2 + par) * 224 + lane;
  uint32_t tg[7];
  if (w > 0) {
    const uint4 v0 = lds128(xa + (w - 1) * 2560), v1 = lds128(xa + (w - 1) * 2560 + 512), v2 = lds128(xa + (w - 1) * 2560 + 1024);
    const uint4 v3 = lds128(xa + (w - 1) * 2560 + 1536), v4 = lds128(xa + (w - 1) * 2560 + 2048);
    kpv[0] = v0.x; kpv[1] = v0.y; kpv[2] = v0.z; kpv[3] = v0.w; kpv[4] = v1.x; kpv[5] = v1.y; kpv[6] = v1.z; kpv[7] = v1.w;
    kpv[8] = v2.x; kpv[9] = v2.y; vpv[0] = v2.z; vpv[1] = v2.w; vpv[2] = v3.x; vpv[3] = v3.y; vpv[4] = v3.z; vpv[5] = v3.w;
    vpv[6] = v4.x; vpv[7] = v4.y; vpv[8] = v4.z; vpv[9] = v4.w;
  } else if (nohist) {
#pragma unroll
    for (int j = 0; j < 10; j++) kpv[j] = vpv[j] = 0u;
  } else {
    TSIF(par == 0, 77);
    halo_read(kpv, vpv, tg, hp);
  }
  if (w == 0 && !nohist) {
    int spins = 0;
    while (true) {
      bool ok = true;
#pragma unroll
      for (int j = 0; j < 7; j++) ok = ok && tg[j] == tag;
      if (__all_sync(0xffffffffu, ok) || ++spins > SPIN_LIMIT) break;
      halo_read(kpv, vpv, tg, hp);
    }
    TSIF(par == 0, 79);
  }
#pragma unroll
  for (int h = 0; h < 4; h++) {
    const int f = h == 0 ? 0 : h == 1 ? 3 : h == 2 ? 5 : 8, hf = h < 2 ? 2 : 7;
    float a[4] = {0.f, 0.f, 0.f, 0.f};
    mma16816(a, qlo[f], qhi[f], qlo[f + 1], qhi[f + 1], kpv[f], kpv[f + 1]);
    mma1688(a, qml[h], qmh[h], kpv[hf]);
    const float ninf = __int_as_float(0xff800000);
    lg[h & 1][0] = far0 ? (nohist ? ninf : a[0]) : slo[h][0];
    lg[h & 1][1] = far1 ? (nohist ? ninf : a[1]) : slo[h][1];
    if (h & 1) {
      softmax_two(lg, plo[h - 1], plo[h]);
      if (ATT_MERGE) {
        const float lh[2][2] = {{shi[h - 1][0], shi[h - 1][1]}, {shi[h][0], shi[h][1]}};
        softmax_two(lh, phi[h - 1], phi[h]);
      }
    }
  }
  TSIF(par == 0 && w <= 1, 67 + w);
  if (ATT_GATE == 2 && lane == 0) mbar_arrive(sb + OFF_BAR + 8 * B_ATT2 + (plo[3] & zero));
  uint32_t ov[20];
#pragma unroll
  for (int hp = 0; hp < 2; hp++) {
    const int hf = hp ? 7 : 2;
    float sh[4] = {0.f, 0.f, 0.f, 0.f}, i0 = 0.f, i1 = 0.f;
#pragma unroll
    for (int e = 0; e < 2; e++) {
      const int h = 2 * hp + e, f = h == 0 ? 0 : h == 1 ? 3 : h == 2 ? 5 : 8;
      const uint32_t a0 = plo[h] & mfar, a2 = plo[h] & ~mfar, a3 = phi[h] & mfar, c1 = phi[h] & ~mfar;
      float sum[4] = {0.f, 0.f, 0.f, 0.f};
      mma1688(sum, plo[h], phi[h], 0x3F803F80u);
      const float r0 = rcp(sum[0]), r1 = rcp(sum[2]);
#pragma unroll
      for (int j = f; j < f + 2; j++) {
        float o[4] = {0.f, 0.f, 0.f, 0.f};
        mma16816(o, a0, 0u, a2, a3, vpv[j], vlo[j]);
        mma1688(o, 0u, c1, vhi[j]);
        ov[2 * j] = pack2(o[0] * r0, o[1] * r0);
        ov[2 * j + 1] = pack2(o[2] * r1, o[3] * r1);
      }
      const bool mine = e ? g >= 4 : g < 4;
      mma16816(sh, a0, 0u, a2, a3, mine ? vpv[hf] : 0u, mine ? vlo[hf] : 0u);
      mma1688(sh, 0u, c1, mine ? vhi[hf] : 0u);
      if (e == 0 || t >= 2) {
        i0 = r0;
        i1 = r1;
      }
    }
    ov[2 * hf] = pack2(sh[0] * i0, sh[1] * i0);
    ov[2 * hf + 1] = pack2(sh[2] * i1, sh[3] * i1);
  }
  if (ATT_GATE == 4 && lane == 0) mbar_arrive(sb + OFF_BAR + 8 * B_ATT2 + (ov[19] & zero));
  TS(32 + 4 * par + w);
  mbar_wait(sb + OFF_BAR + 8 * B_P1, 0);
  const uint32_t oa = sb + OFF_OA + (lane >> 4) * 2048 + (32 * w + 2 * (lane & 15) + par) * 16;
#pragma unroll
  for (int j = 0; j < 5; j++) stsm4(oa + 4096 * j, ov + 4 * j);
  TSIF(par == 0 && w == 0, 120);
  fence_async_smem();
  TSIF(par == 0 && w == 0, 121);
  __syncwarp();
  if (lane == 0) mbar_arrive(sb + OFF_BAR + 8 * B_ATTN);
  TSM(w == 0 || w == 2, 122 + par + (w == 2 ? 3 : 0));
}

struct Maps {
  CUtensorMap x, wm, wt, k, v, y, wo, qm, qt, om, ot, u;
};

__device__ __forceinline__ void load_stage(uint32_t sb, int kb, int b, const Maps& m) {
  const uint32_t st = sb + (kb & 3) * STAGE_BYTES, bar = sb + OFF_BAR + 8 * (B_FULL1 + (kb & 3));
  const int r = b >> 3, hg = b & 7, slab = kb - KV_KB;
  const bool kv = slab >= 0 && slab < 5;
  const uint32_t kbar = sb + OFF_BAR + 8 * (B_KV + slab), dst = sb + OFF_KVS + slab * KVS_BYTES;
  mbar_expect_tx(bar, STAGE_BYTES);
  if (kv) mbar_expect_tx(kbar, KVS_BYTES);
  tma_3d(st, &m.x, 64 * kb, 64 * r, 0, bar);
  if (kv && KV_MIX) tma_3d(dst, &m.k, 0, 32 * (b >> 1) - 3, 2 * slab + (b & 1), kbar);
  tma_3d(st + ST_W, &m.wm, 80 * hg + (tail_first(hg) ? 16 : 0), 64 * kb, 0, bar);
  if (kv && KV_MIX) tma_3d(dst + KVS_V, &m.v, 0, 32 * (b >> 1), 2 * slab + (b & 1), kbar);
  tma_3d(st + ST_WT, &m.wt, 80 * hg + (tail_first(hg) ? 0 : 64), 64 * kb, 0, bar);
  if (kv && !KV_MIX) tma_3d(dst, &m.k, 0, 32 * (b >> 1) - 3, 2 * slab + (b & 1), kbar);
  if (kv && !KV_MIX) tma_3d(dst + KVS_V, &m.v, 0, 32 * (b >> 1), 2 * slab + (b & 1), kbar);
}

__global__ void __launch_bounds__(NTHR, 1) fused_kernel(const __grid_constant__ Maps m, const Params p) {
  extern __shared__ __align__(1024) uint8_t smem[];
  const uint32_t sb = (uint32_t)__cvta_generic_to_shared(smem);
  const uint32_t bars = sb + OFF_BAR;
  const int tid = threadIdx.x, lane = tid & 31;
  int b = blockIdx.x;
  if (BMAP == 1) b = (((b & 63) >> 3) * 2 + (b & 1)) * 8 + (((b < 64 ? 0x6521 : 0x7430) >> (4 * ((b >> 1) & 3))) & 7);
  if (BMAP == 2) b = ((b & 63) >> 2) * 8 + (((b < 64 ? 0x6521 : 0x7430) >> (4 * (b & 3))) & 7);
  if (BMAP == 3) b = (((b & 63) >> 3) * 2 + (b & 1)) * 8 + (((b < 64 ? 0x7430 : 0x6521) >> (4 * ((b >> 1) & 3))) & 7);
  if (BMAP == 4) b = (((b >> 4) * 2 + (b & 1)) * 8) + ((b >> 1) & 7);
  if (BMAP == 5) b = 127 - b;
  const int r = b >> 3, hg = b & 7;

  if (tid == T_ISSUE) {
    TSM(true, 0);
    mbar_init(bars + 8 * B_F0, 1);
    if (!FAST0) {
#pragma unroll
      for (int i = 0; i < 4; i++) mbar_init(bars + 8 * (B_FULL1 + i), 1);
    }
    fence_async_smem();
    mbar_expect_tx(bars + 8 * B_F0, ST_WT);
    tma_3d(sb, &m.x, 0, 64 * r, 0, bars + 8 * B_F0);
    tma_3d(sb + ST_W, &m.wm, 80 * hg + (tail_first(hg) ? 16 : 0), 0, 0, bars + 8 * B_F0);
    if (FAST0) {
#pragma unroll
      for (int i = 0; i < 4; i++) mbar_init(bars + 8 * (B_FULL1 + i), 1);
      fence_async_smem();
    }
    mbar_expect_tx(bars + 8 * B_FULL1, STAGE_BYTES - ST_WT);
    tma_3d(sb + ST_WT, &m.wt, 80 * hg + (tail_first(hg) ? 0 : 64), 0, 0, bars + 8 * B_FULL1);
    load_stage(sb, 1, b, m);
  } else if (tid >= T_PF && tid < T_PF + 12) {
    tm_prefetch(&m.x + (tid - T_PF));
  } else if (tid == T_INIT) {
#pragma unroll
    for (int i = 0; i < 4; i++) mbar_init(bars + 8 * (B_EMPTY1 + i), 8);
#pragma unroll
    for (int i = 0; i < 8; i++) mbar_init(bars + 8 * (B_FULL2 + i), 1);
#pragma unroll
    for (int i = 0; i < 4; i++) mbar_init(bars + 8 * (B_EMPTY2 + i), 8);
#pragma unroll
    for (int i = 0; i < 4; i++) mbar_init(bars + 8 * (B_U + i), 1);
    mbar_init(bars + 8 * B_HA, 4);
    mbar_init(bars + 8 * B_GATE, 4);
    mbar_init(bars + 8 * B_HB, 1);
    mbar_init(bars + 8 * B_KVD, 4);
    mbar_init(bars + 8 * B_QF, 1);
    mbar_init(bars + 8 * B_ATTN, 8);
    mbar_init(bars + 8 * B_ATT2, 8);
    mbar_init(bars + 8 * B_P1, 8);
    mbar_init(bars + 8 * B_C34, 1);
    mbar_init(bars + 8 * B_YRB, 1);
#pragma unroll
    for (int i = 0; i < 5; i++) mbar_init(bars + 8 * (B_YST + i), 4);
#pragma unroll
    for (int i = 0; i < 3; i++) mbar_init(bars + 8 * (B_US + i), U_TMA ? 4 : i == 2 ? 20 : 1);
    mbar_init(bars + 8 * B_YSIG, 1);
    mbar_init(bars + 8 * B_YFULL, 1);
    mbar_init(bars + 8 * B_EPOCH, 1);
    mbar_init(bars + 8 * B_PREP, 4);
    mbar_init(bars + 8 * B_USIG, 1);
    mbar_init(bars + 8 * B_WST, 1);
#pragma unroll
    for (int i = 0; i < 5; i++) mbar_init(bars + 8 * (B_KV + i), 1);
    mbar_init(bars + 8 * B_E3, 8);
    mbar_init(bars + 8 * B_LAST, 1);
    mbar_init(bars + 8 * B_OSIG, 1);
    mbar_init(bars + 8 * B_WOP, 1);
    fence_async_smem();
  }
  const int warp = __shfl_sync(0xffffffffu, tid >> 5, 0), wg = warp >> 2, w = warp & 3;
  __syncthreads();

  if (wg == 3) {
    asm volatile("setmaxnreg.dec.sync.aligned.u32 56;");
    if (w == 0) {
      if (lane == 0) {
#pragma unroll 1
        for (int kb = 2; kb < 10; kb++) {
          if (kb >= 4) mbar_wait(bars + 8 * (kb == 7 ? B_E3 : B_EMPTY1 + (kb & 3)), (kb >> 3) & 1);
          TSIF(kb >= 4, 44 + kb);
          load_stage(sb, kb, b, m);
          TSIF(kb == 3, 60);
          if (kb == TRIG_KB) mbar_arrive(bars + 8 * B_LAST);
        }
        mbar_wait(bars + 8 * B_WOP, 0);
        mbar_wait(bars + 8 * WL_TRIG, 0);
        mbar_wait(bars + 8 * B_EPOCH, 0);
        flag_wait(g_cnt + C_W + 32 * hg, (lds32(sb + OFF_EPOCH) + 1) * 16);
        TS(30);
#pragma unroll 1
        for (int j = 0; j < 8; j++) {
          if (j >= 6) mbar_wait(bars + 8 * (B_EMPTY2 + j - 6), 0);
          if (j == 4) mbar_wait(bars + 8 * B_ATTN, 0);
          TSIF(j >= 6, 100 + j);
          if (RF_GATE && j == 6) mbar_wait(bars + 8 * B_YSIG, 0);
          mbar_expect_tx(bars + 8 * (B_FULL2 + j), j == 0 ? WO_BYTES : j == 5 ? O_BYTES + WO_BYTES + 512 : O_BYTES + WO_BYTES);
          bulk_load(sb + off_w(j), g_WO + (hg * 8 + step_src(hg, j)) * 800, WO_BYTES, bars + 8 * (B_FULL2 + j));
        }
        mbar_wait(bars + 8 * (B_EMPTY2 + Q_SLOT), 0);
        mbar_expect_tx(bars + 8 * B_QF, O_BYTES);
        tma_2d(sb + OFF_QS, &m.qm, 80 * hg, 128 * r, bars + 8 * B_QF);
        if (!QBOX) tma_2d(sb + OFF_QT, &m.qt, 80 * hg + 64, 128 * r, bars + 8 * B_QF);
      }
    } else if (w == 1) {
      unsigned epoch = 0;
      if (lane == 0) {
        epoch = atomicAdd(g_cnt + C_LAUNCH, 1u) / NCTA;
        asm volatile("st.shared.u32 [%0], %1;" ::"r"(sb + OFF_EPOCH), "r"(epoch) : "memory");
        mbar_arrive(bars + 8 * B_EPOCH);
        mbar_wait(bars + 8 * B_KVD, 0);
        mbar_expect_tx(bars + 8 * B_HB, 5 * 4096);
#pragma unroll 1
        for (int c = 0; c < 5; c++) {
          if (c == 3) mbar_wait(bars + 8 * B_S3, 0);
          bulk_load(sb + off_ch(c) + U_BYTES, p.ssm_k + (5 * b + c) * SEQ, 4096, bars + 8 * B_HB);
        }
#pragma unroll
        for (int c = 0; c < 4; c++) mbar_expect_tx(bars + 8 * (B_U + c), c < 3 ? U_BYTES : 2 * U_BYTES);
        const uint4* usrc = g_U + 5 * b * U_PITCH;
        mbar_wait(bars + 8 * B_USIG, 0);
        flag_wait(g_cnt + C_PREP + 32 * (b & 15), (epoch + 1) * NCTA);
        TS(23);
#pragma unroll
        for (int c = 0; c < 5; c++) {
          if (c == 3 && U_TRIM) mbar_wait(bars + 8 * (B_U + 2), 0);
          bulk_load(sb + off_ch(c), usrc + c * U_PITCH, U_BYTES, bars + 8 * (B_U + (c < 3 ? c : 3)));
          TSIF(c == 0 || c == 4, 116 + (c >> 2));
        }
      }
      epoch = __shfl_sync(0xffffffffu, epoch, 0);
      if (lane < 8) {
        const int src = (b & ~7) | step_src(hg, lane);
        mbar_wait(bars + 8 * OP_TRIG, 0);
        TS(20);
        bool seen = false;
#pragma unroll 1
        for (int spins = 0; spins < SPIN_LIMIT; spins++) {
          const bool now = !seen && (int)(flag_read(g_cnt + C_O + 32 * src) - (epoch + 1)) >= 0;
          if (now && lane >= 1 && lane < 4) bulk_load(sb + off_o(lane), g_O + src * 1280, O_BYTES, bars + 8 * (B_FULL2 + lane));
          seen = seen || now;
          if (__all_sync(0xff, seen)) break;
        }
        TS(21);
        if (lane == 5) bulk_load(sb + OFF_GATE, g_gate + 128 * r, 512, bars + 8 * (B_FULL2 + 5));
#pragma unroll 1
        for (int j = 4; j < 8; j++) {
          if (lane == j) {
            mbar_wait(bars + 8 * (j < 6 ? B_C34 : B_EMPTY2 + j - 6), 0);
            if (RF_GATE && j == 6) mbar_wait(bars + 8 * B_YSIG, 0);
            bulk_load(sb + off_o(j), g_O + src * 1280, O_BYTES, bars + 8 * (B_FULL2 + j));
          }
          __syncwarp(0xff);
        }
        TS(22);
      }
    } else if (w == 2) {
      mbar_wait(bars + 8 * B_PREP, 0);
      flag_signal(g_cnt + C_PREP, 16, lane);
      TS(25);
      if (lane == 0) mbar_arrive(bars + 8 * B_USIG);
      mbar_wait(bars + 8 * B_GATE, 0);
      if (G_TMA) {
        if (lane == 0) {
          asm volatile("cp.async.bulk.global.shared::cta.bulk_group [%0], [%1], 64;\ncp.async.bulk.commit_group;\n"
                       "cp.async.bulk.wait_group.read 0;" ::"l"(g_gate + 16 * b), "r"(sb + OFF_GATE + 64 * hg) : "memory");
          bulk_load(sb + OFF_GATE + 64 * hg, g_gate + 16 * b, 64, bars + 8 * B_ORB);
        }
      } else if (((NOMB & 1) || O_RB) && lane == 0) {
        asm volatile("fence.release.gpu;" ::: "memory");
      }
      mbar_wait(bars + 8 * B_ATTN, 0);
      if (lane == 0) {
        if (O_DEFER) mbar_wait(bars + 8 * (B_U + 3), 0);
        asm volatile("cp.async.bulk.global.shared::cta.bulk_group [%0], [%1], 20480;\ncp.async.bulk.commit_group;"
                     ::"l"(g_O + b * 1280), "r"(sb + OFF_OA) : "memory");
        if (O_RB == 2) {
          asm volatile("cp.async.bulk.wait_group.read 0;" ::: "memory");
          mbar_expect_tx(bars + 8 * B_ORB, O_BYTES + 64 * G_TMA);
          bulk_load(sb + OFF_OA, g_O + b * 1280, O_BYTES, bars + 8 * B_ORB);
          mbar_wait(bars + 8 * B_ORB, 0);
          flag_bump(g_cnt + C_O + 32 * b);
        } else if (O_RB) asm volatile("cp.async.bulk.wait_group.read 0;" ::: "memory");
        else asm volatile("cp.async.bulk.wait_group 0;\nfence.proxy.async.global;" ::: "memory");
      }
      TS(74);
      if (O_RB == 2) {
      } else if (O_RB) {
        __syncwarp();
        unsigned v[5];
#pragma unroll
        for (int c = 0; c < 5; c++) v[c] = flag_read(reinterpret_cast<const unsigned*>(g_O + b * 1280 + 256 * c + 8 * lane + 7));
        const unsigned dep = __reduce_or_sync(0xffffffffu, (v[0] ^ v[1] ^ v[2] ^ v[3] ^ v[4]) & p.zero);
        if (lane == 0) flag_bump(g_cnt + C_O + 32 * b + dep);
      } else if (!(NOMB & 1)) flag_signal(g_cnt + C_O + 32 * b, 1, lane);
      else if (lane == 0) flag_bump(g_cnt + C_O + 32 * b);
      TS(26);
      if (lane == 0) mbar_arrive(bars + 8 * B_OSIG);

    } else {
      if (lane == 0) {
        uint4* dst = g_WO + (hg * 8 + (r >> 1)) * 800 + (r & 1) * 80;
        if (WPF) {
          mbar_wait(bars + 8 * WPF, 0);
          if (WPF_LIN)
            asm volatile("cp.async.bulk.prefetch.L2.global [%0], 6400;" ::"l"(p.wo + b * 3200) : "memory");
          else
            asm volatile("cp.async.bulk.prefetch.tensor.3d.L2.global [%0, {%1, %2, %3}];" ::"l"(&m.wo), "r"(0), "r"(40 * r), "r"(5 * hg) : "memory");
        }
        mbar_wait(bars + 8 * B_P1, 0);
        mbar_wait(bars + 8 * WB_TRIG, 0);
        mbar_expect_tx(bars + 8 * B_WST, WO_BYTES / 2);
        tma_3d(sb + OFF_WS, &m.wo, 0, 40 * r, 5 * hg, bars + 8 * B_WST);
        mbar_wait(bars + 8 * B_WST, 0);
        mbar_wait(bars + 8 * WO_TRIG, 0);
#pragma unroll 1
        for (int n = 0; n < 5; n++)
          asm volatile("cp.async.bulk.global.shared::cta.bulk_group [%0], [%1], 1280;" ::"l"(dst + 160 * n), "r"(sb + OFF_WS + 1280 * n) : "memory");
        if (W_RB) {
          asm volatile("cp.async.bulk.commit_group;\ncp.async.bulk.wait_group.read 0;" ::: "memory");
          mbar_expect_tx(bars + 8 * B_WST, WO_BYTES / 2);
#pragma unroll 1
          for (int n = 0; n < 5; n++) bulk_load(sb + OFF_WS + 1280 * n, dst + 160 * n, 1280, bars + 8 * B_WST);
          mbar_wait(bars + 8 * B_WST, 1);
        } else {
          asm volatile("cp.async.bulk.commit_group;\ncp.async.bulk.wait_group 0;\nfence.proxy.async.global;" ::: "memory");
          if (!(NOMB & 4)) asm volatile("fence.release.gpu;" ::: "memory");
        }
        flag_bump(g_cnt + C_W + 32 * hg);
        mbar_arrive(bars + 8 * B_WOP);
        TS(71);
        mbar_expect_tx(bars + 8 * B_C34, 3 * U_BYTES);
        mbar_expect_tx(bars + 8 * B_YRB, 2 * U_BYTES);
#pragma unroll 1
        for (int c = 0; c < 5; c++) {
          mbar_wait(bars + 8 * (B_YST + c), 0);
          asm volatile("cp.async.bulk.global.shared::cta.bulk_group [%0], [%1], 4096;\ncp.async.bulk.commit_group;\n"
                       "cp.async.bulk.wait_group.read 0;" ::"l"(g_Y + (5 * b + c) * Y_PITCH), "r"(sb + off_ch(c)) : "memory");
          bulk_load(sb + off_ch(c), g_Y + (5 * b + c) * Y_PITCH, U_BYTES, bars + 8 * (c < 3 ? B_C34 : B_YRB));
        }
        TS(75);
        mbar_wait(bars + 8 * B_C34, 0);
        mbar_wait(bars + 8 * B_YRB, 0);
        flag_bump(g_cnt + C_Y + 32 * (b >> 4));
        TS(27);
        mbar_arrive(bars + 8 * B_YSIG);
        mbar_expect_tx(bars + 8 * B_YFULL, 20480);
        flag_wait(g_cnt + C_Y + 32 * hg, (lds32(sb + OFF_EPOCH) + 1) * 16);
        TS(24);
        tma_2d(sb + OFF_YT, &m.y, 128 * r, 80 * hg, bars + 8 * B_YFULL);
        tma_2d(sb + OFF_YT + 10240, &m.y, 128 * r + 64, 80 * hg, bars + 8 * B_YFULL);
      }
    }
  } else {
    asm volatile("setmaxnreg.inc.sync.aligned.u32 152;");
    if (wg < 2) {
      float acc[120];
#pragma unroll
      for (int i = 0; i < 120; i++) acc[i] = 0.f;
      const uint32_t da = desc_lo(sb + wg * 8192, 16), db = desc_lo(sb + ST_W, 8192), dc = desc_lo(sb + ST_WT, 2048);
      mbar_wait(bars + 8 * B_F0, 0);
      TSIF(w == 0 && wg == 0, 1);
      wg_fence();
#pragma unroll
      for (int k = 0; k < 4; k++) WgSST<192>::mma<HI_SW128, HI_SW128>(acc, da + 2 * k, db + 128 * k, 1);
      wg_commit();
      mbar_wait(bars + 8 * B_FULL1, 0);
      wg_fence();
#pragma unroll
      for (int k = 0; k < 4; k++) WgSST<48>::mma<HI_SW128, HI_SW32>(acc + 96, da + 2 * k, dc + 32 * k, 1);
      wg_commit();
#pragma unroll 1
      for (int kb = 1; kb < 10; kb++) {
        mbar_wait(bars + 8 * (B_FULL1 + (kb & 3)), (kb >> 2) & 1);
        const uint32_t so = (kb & 3) * (STAGE_BYTES >> 4);
        wg_fence();
#pragma unroll
        for (int k = 0; k < 4; k++) {
          WgSST<192>::mma<HI_SW128, HI_SW128>(acc, da + so + 2 * k, db + so + 128 * k, 1);
          WgSST<48>::mma<HI_SW128, HI_SW32>(acc + 96, da + so + 2 * k, dc + so + 32 * k, 1);
        }
        wg_commit();
        wg_wait<1>();
        if (lane == 0) mbar_arrive(bars + 8 * (kb == 4 ? B_E3 : B_EMPTY1 + ((kb - 1) & 3)));
      }
      mbar_wait(bars + 8 * B_EPOCH, 0);
      const uint32_t tag = lds32(sb + OFF_EPOCH) + 1;
      mbar_wait(bars + 8 * B_S3, 0);
      wg_wait<0>();
      pin<120>(acc);
      if (lane == 0) mbar_arrive(bars + 8 * B_P1);
      TSM(w == 0, 3 + wg);
      attention(acc, sb, b, wg, w, lane, tag, p.zero);
    } else {
      const int tw = tid & 127, chl = 64 * (b & 1) + 8 * w + (lane >> 2);
      uint4* up = g_U + chl * U_PITCH + ((4 * (b >> 1) + (lane & 3)) ^ ((b >> 2) & 1));
      uint2 sw[10];
      uint32_t dv = 0;
      if (lane < 5) dv = __ldg(reinterpret_cast<const unsigned short*>(p.ssm_D) + 5 * b + lane);
#pragma unroll
      for (int i = 0; i < 10; i++) sw[i] = ldg64(reinterpret_cast<const uint2*>(p.shift_k) + chl + 128 * (i >> 1) + 32 * (i & 1));
      uint32_t tab[12];
      uint32_t tt[2];
      fft_tables(tab, tw);
      fft_twiddles(tt, tw);
      uint4 res[10];
#pragma unroll
      for (int i = 0; i < 10; i++) res[i] = make_uint4(0, 0, 0, 0);
#pragma unroll 1
      for (int slab = 0; slab < 5; slab++) {
#pragma unroll
        for (int i = 0; i < 8; i++) res[i] = res[i + 2];
        prep_slab(res + 8, sw, sb, slab, w, lane);
        TSIF(w == 0, 99 + 4 * slab);
#pragma unroll
        for (int i = 0; i < 8; i++) sw[i] = sw[i + 2];
      }
      TSIF(w == 0, 28);
      __syncwarp();
      if (lane == 0) mbar_arrive(bars + 8 * B_KVD + ((res[8].x ^ res[9].x) & p.zero));
      mbar_wait(bars + 8 * B_KVD, 0);
      fft_tables_store(tab, sb, tw);
      mbar_wait(bars + 8 * B_LAST, 0);
#pragma unroll
      for (int i = 0; i < 10; i++) up[(128 * (i >> 1) + 32 * (i & 1)) * U_PITCH] = res[i];
      __syncwarp();
      if (lane == 0) mbar_arrive(bars + 8 * B_PREP);
      TSIF(w == 0 && !U_TMA, 5);
      mbar_wait(bars + 8 * (G_AFTER ? B_USIG : B_LAST), 0);
      prep_gate(p, sb, b, w, lane);
      __syncwarp();
      if (lane == 0) mbar_arrive(bars + 8 * B_GATE);
      TSIF(w == 0, 72);
      mbar_wait(bars + 8 * B_HB, 0);
      TSIF(w == 0, 2);
      const uint32_t ha = sb + U_BYTES + ((tw >> 3) * 16 + 8 + (tw & 7)) * 16;
      uint4 hv[5];
#pragma unroll
      for (int c = 0; c < 5; c++) hv[c] = lds128(ha + off_ch(c));
      __syncwarp();
#pragma unroll
      for (int c = 0; c < 5; c++) sts128((ha ^ 16) + off_ch(c), hv[c].x, hv[c].y, hv[c].z, hv[c].w);
      asm volatile("st.shared.v2.u32 [%0], {%1, %2};" ::"r"(sb + OFF_TT + 8 * tw), "r"(tt[0]), "r"(tt[1]) : "memory");
      if (tw < 5) asm volatile("st.shared.f32 [%0], %1;" ::"r"(sb + OFF_D + 4 * tw), "f"(bf_lo(dv) * 0.125f) : "memory");
      fence_async_smem();
      __syncwarp();
      if (lane == 0) mbar_arrive(bars + 8 * B_HA);
      TSIF(w == 0, 6);
    }

    FftConst fc;
    TSM(w == 0 && wg == 0, 104);
    mbar_wait(bars + 8 * B_HA, 0);
    fft_matrices(fc, sb, w, lane);
    TSM(w == 0 && wg == 0, 105);
    TSM(w == 0 && wg == 2, 124);
#pragma unroll 1
    for (uint32_t tasks = wg == 0 ? TASK0 : wg == 1 ? TASK1 : TASK2; tasks; tasks >>= 4) {
      const int c = (tasks & 7) - 1;
      conv_channel(fc, sb, c, wg, w, lane);
      if (lane == 0) mbar_arrive(bars + 8 * (B_YST + c));
      TSM(w == 0, 10 + c);
    }

    if (wg < 2) {
      const int g = lane >> 2;
      float acc[40];
#pragma unroll
      for (int i = 0; i < 40; i++) acc[i] = 0.f;
      const uint32_t da = desc_lo(sb + wg * 1024, 2048), db = desc_lo(sb, 2560);
      mbar_wait(bars + 8 * (O_RB == 2 ? B_ORB : B_ATTN), 0);
      if (PW2) mbar_wait(bars + 8 * B_FULL2, 0);
      mbar_wait(bars + 8 * B_CVD, 0);
      TSM(w == 0, 15 + wg);
#pragma unroll 1
      for (int j = 0; j < 8; j++) {
        mbar_wait(bars + 8 * (B_FULL2 + j), 0);
        TSM(w == 0 && wg == 0, 44 + (j < 4 ? j : j + 6));
        const uint32_t oa = da + (off_o(j) >> 4), ob = db + (off_w(j) >> 4);
        wg_fence();
#pragma unroll
        for (int k = 0; k < 5; k++) WgSST<80>::mma<HI_NONE, HI_SW32>(acc, oa + 256 * k, ob + 32 * k, 1);
        wg_commit();
        wg_wait<1>();
        if (j >= 1 && j <= Q_SLOT + 1 && lane == 0) mbar_arrive(bars + 8 * (B_EMPTY2 + j - 1));
      }
      TSIF(w == 0 && wg == 0, 113);
      const int tr = 64 * wg + 16 * w + (lane & 15);
      const uint32_t fm = sb + OFF_QS + tr * 128, fx = (lane >> 4) ^ (tr & 7), fq = sb + OFF_QS + tr * 160 + (lane >> 4) * 16;
      const uint32_t ft = sb + OFF_QT + tr * 32 + (((lane >> 4) ^ (tr >> 2)) & 1) * 16;
      const float g0 = __uint_as_float(lds32(sb + OFF_GATE + (64 * wg + 16 * w + g) * 4));
      const float g1 = __uint_as_float(lds32(sb + OFF_GATE + (64 * wg + 16 * w + 8 + g) * 4));
      const uint32_t ga = pack2(g0, g0), gb = pack2(g1, g1);
      const uint32_t na = pack2(1.f - g0, 1.f - g0), nb = pack2(1.f - g1, 1.f - g1);

      uint32_t qf[20];
      mbar_wait(bars + 8 * B_QF, 0);
      TSM(w == 0 && wg == 0, 99);
#pragma unroll
      for (int j = 0; j < 5; j++) ldsm4(qf + 4 * j, QBOX ? fq + 32 * j : j < 4 ? fm + ((fx ^ (2 * j)) << 4) : ft);
      if (FUSE_MIX) {
#pragma unroll
        for (int i = 0; i < 20; i++) {
          qf[i] = bmul((i & 1) ? gb : ga, qf[i]);
          asm volatile("" : "+r"(qf[i]));
        }
      }
      wg_wait<0>();
      pin<40>(acc);
      TSM(w == 0, 17 + wg);
      uint32_t pb[20];
#pragma unroll
      for (int j = 0; j < 10; j++) {
        pb[2 * j] = bmul(na, pack2(acc[4 * j], acc[4 * j + 1]));
        pb[2 * j + 1] = bmul(nb, pack2(acc[4 * j + 2], acc[4 * j + 3]));
        asm volatile("" : "+r"(pb[2 * j]), "+r"(pb[2 * j + 1]));
      }
      const uint32_t ya = sb + OFF_YT + wg * 10240 + ((lane >> 4) * 8 + (lane & 7)) * 128 +
                          (((2 * w + (((lane >> 3) & 1) ^ wg)) ^ (lane & 7)) << 4);
      mbar_wait(bars + 8 * B_YFULL, 0);
      TSM(w == 0 && wg == 0, 19);
#pragma unroll
      for (int j = 0; j < 5; j++) {
        uint32_t y[4];
        ldsm4t(y, ya + 2048 * j);
#pragma unroll
        for (int i = 0; i < 4; i++)
          qf[4 * j + i] = FUSE_MIX ? bfma(qf[4 * j + i], y[i], pb[4 * j + i]) : badd(bmul((i & 1) ? gb : ga, bmul(qf[4 * j + i], y[i])), pb[4 * j + i]);
      }
#pragma unroll
      for (int j = 0; j < 5; j++) stsm4(QBOX ? fq + 32 * j : j < 4 ? fm + ((fx ^ (2 * j)) << 4) : ft, qf + 4 * j);
      fence_async_smem();
      __syncwarp();
      if (lane == 0) {
        const int row = 64 * wg + 16 * w;
        asm volatile("cp.async.bulk.tensor.2d.global.shared::cta.bulk_group [%0, {%2, %3}], [%1];"
                     ::"l"(&m.om), "r"(sb + OFF_QS + row * (QBOX ? 160 : 128)), "r"(80 * hg), "r"(128 * r + row) : "memory");
        if (!QBOX) asm volatile("cp.async.bulk.tensor.2d.global.shared::cta.bulk_group [%0, {%2, %3}], [%1];"
                     ::"l"(&m.ot), "r"(sb + OFF_QT + row * 32), "r"(80 * hg + 64), "r"(128 * r + row) : "memory");
        asm volatile("cp.async.bulk.commit_group;\ncp.async.bulk.wait_group.read 0;" ::: "memory");
      }
      TSM(w == 0 || w == 3, 40 + 2 * wg + (w & 1));
      if (ENDBAR) asm volatile("bar.sync 15, 256;" ::: "memory");
    }
  }
}

typedef CUresult (*EncodeFn)(CUtensorMap*, CUtensorMapDataType, cuuint32_t, void*, const cuuint64_t*, const cuuint64_t*,
                             const cuuint32_t*, const cuuint32_t*, CUtensorMapInterleave, CUtensorMapSwizzle,
                             CUtensorMapL2promotion, CUtensorMapFloatOOBfill);

void encode(EncodeFn fn, CUtensorMap* tm, const void* base, int rank, const cuuint64_t* dims, const cuuint64_t* strides,
            const cuuint32_t* box, CUtensorMapSwizzle swz) {
  const cuuint32_t ones[3] = {1, 1, 1};
  fn(tm, CU_TENSOR_MAP_DATA_TYPE_BFLOAT16, rank, const_cast<void*>(base), dims, strides, box, ones,
     CU_TENSOR_MAP_INTERLEAVE_NONE, swz, CU_TENSOR_MAP_L2_PROMOTION_L2_128B, CU_TENSOR_MAP_FLOAT_OOB_FILL_NONE);
}

}

extern "C" void kernel_launch(void* const* d_in, const int* in_sizes, int n_in, void* d_out, int out_size) {
  (void)in_sizes; (void)n_in; (void)out_size;
  Params p;
  p.q = (const __nv_bfloat16*)d_in[0];
  p.k = (const __nv_bfloat16*)d_in[1];
  p.v = (const __nv_bfloat16*)d_in[2];
  p.shift_k = (const __nv_bfloat16*)d_in[3];
  p.ssm_k = (const __nv_bfloat16*)d_in[4];
  p.ssm_D = (const __nv_bfloat16*)d_in[5];
  p.wqkv = (const __nv_bfloat16*)d_in[7];
  p.wo = (const __nv_bfloat16*)d_in[8];
  p.gate_w = (const __nv_bfloat16*)d_in[9];
  p.out = (__nv_bfloat16*)d_out;
  p.zero = 0;

  static EncodeFn fn = nullptr;
  static void *yaddr = nullptr, *uaddr = nullptr;
  if (!fn) {
    cudaDriverEntryPointQueryResult qr;
    void* f = nullptr;
    cudaGetDriverEntryPoint("cuTensorMapEncodeTiled", &f, cudaEnableDefault, &qr);
    fn = (EncodeFn)f;
    cudaGetSymbolAddress(&yaddr, g_Y);
    cudaGetSymbolAddress(&uaddr, g_U);
    cudaFuncSetAttribute(fused_kernel, cudaFuncAttributeMaxDynamicSharedMemorySize, SMEM_BYTES);
  }
  Maps m;
  {
    const cuuint64_t dims[3] = {640, 1024, 2}, st[2] = {2560, 1280};
    const cuuint32_t box[3] = {64, 64, 2};
    encode(fn, &m.x, p.q, 3, dims, st, box, CU_TENSOR_MAP_SWIZZLE_128B);
  }
  {
    const cuuint64_t dims[3] = {640, 640, 3}, st[2] = {3840, 1280};
    const cuuint32_t box[3] = {64, 64, 3}, boxt[3] = {16, 64, 3};
    encode(fn, &m.wm, p.wqkv, 3, dims, st, box, CU_TENSOR_MAP_SWIZZLE_128B);
    encode(fn, &m.wt, p.wqkv, 3, dims, st, boxt, CU_TENSOR_MAP_SWIZZLE_32B);
  }
  {
    const cuuint64_t dims[3] = {64, 2048, 10}, st[2] = {1280, 128};
    const cuuint32_t boxk[3] = {64, 35, 1}, boxv[3] = {64, 32, 1};
    encode(fn, &m.k, p.k, 3, dims, st, boxk, CU_TENSOR_MAP_SWIZZLE_128B);
    encode(fn, &m.v, p.v, 3, dims, st, boxv, CU_TENSOR_MAP_SWIZZLE_128B);
  }
  {
    const cuuint64_t dims[3] = {16, 640, 40}, st[2] = {1280, 32};
    const cuuint32_t box[3] = {16, 40, 5};
    encode(fn, &m.wo, p.wo, 3, dims, st, box, CU_TENSOR_MAP_SWIZZLE_32B);
  }
  {
    const cuuint64_t dims[2] = {2048, 640}, st[1] = {Y_PITCH * 16};
    const cuuint32_t box[2] = {64, 80};
    encode(fn, &m.y, yaddr, 2, dims, st, box, CU_TENSOR_MAP_SWIZZLE_128B);
    const cuuint64_t stu[1] = {U_PITCH * 16};
    const cuuint32_t boxu[2] = {32, 64};
    encode(fn, &m.u, uaddr, 2, dims, stu, boxu, CU_TENSOR_MAP_SWIZZLE_NONE);
  }
  {
    const cuuint64_t dims[2] = {640, 2048}, st[1] = {1280};
    const cuuint32_t bqm[2] = {QBOX ? 80 : 64, 128}, bqt[2] = {16, 128}, bom[2] = {QBOX ? 80 : 64, 16}, bot[2] = {16, 16};
    encode(fn, &m.qm, p.q, 2, dims, st, bqm, QBOX ? CU_TENSOR_MAP_SWIZZLE_NONE : CU_TENSOR_MAP_SWIZZLE_128B);
    encode(fn, &m.qt, p.q, 2, dims, st, bqt, CU_TENSOR_MAP_SWIZZLE_32B);
    encode(fn, &m.om, p.out, 2, dims, st, bom, QBOX ? CU_TENSOR_MAP_SWIZZLE_NONE : CU_TENSOR_MAP_SWIZZLE_128B);
    encode(fn, &m.ot, p.out, 2, dims, st, bot, CU_TENSOR_MAP_SWIZZLE_32B);
  }
  fused_kernel<<<NCTA, NTHR, SMEM_BYTES>>>(m, p);
}
```

```cpp
#include <cuda.h>
#include <cuda_bf16.h>
#include <cuda_runtime.h>
#include <stdint.h>

namespace {

constexpr int SEQ = 2048, DIM = 640, NCTA = 128, NTHR = 512;

#define TRIG_KB 9
#define KV_KB 2
#define DEV_EXIT 0
#define FENCE_LO 0
#define FENCE_HI 0
#define WB_TRIG B_USIG
#define T_ISSUE 256
#define T_INIT 448
#define TASK0 0x3
#define TASK1 0x52
#define TASK2 0x41
#define WL_TRIG B_WOP

constexpr uint32_t STAGE_BYTES = 47104, ST_W = 16384, ST_WT = 40960;
constexpr uint32_t O_BYTES = 20480, WO_BYTES = 12800;
constexpr uint32_t OFF_OA = 0;
constexpr uint32_t OFF_QS = 3 * O_BYTES, OFF_QT = OFF_QS + 16384;
constexpr uint32_t OFF_WC = 81920;
constexpr uint32_t OFF_WA = 94720;
constexpr uint32_t OFF_GATE = 145920;
constexpr uint32_t OFF_TT = 146432;
constexpr uint32_t OFF_KVX = 148480;
constexpr uint32_t OFF_CH3 = 163840;
constexpr uint32_t CH_BYTES = 12288, U_BYTES = 4096;
constexpr uint32_t OFF_FT = 225280, OFF_GT = 229376;
constexpr uint32_t OFF_CH0 = 188416;
constexpr uint32_t OFF_KVS = OFF_CH0, KVS_V = 4480, KVS_BYTES = 8576;
constexpr uint32_t OFF_YT = 163840;
constexpr uint32_t OFF_BAR = 231936;
constexpr uint32_t SMEM_BYTES = OFF_BAR + 512;

enum : uint32_t {
  B_EMPTY1 = 0, B_S3 = 3, B_E3 = 4, B_EMPTY2 = 5, B_ATTN = 9, B_P1 = 10,
  B_GATE = 11, B_HA = 12, B_KVD = 13, B_PREP = 14, B_YST = 15,
  B_CVD = 20,
  B_FULL2 = 21, B_U = 29, B_KV = 33, B_HB = 38, B_C34 = 39, B_YRB = 40, B_YFULL = 41, B_EPOCH = 42, B_LAST = 43, B_OSIG = 44,
  B_WOP = 45, B_USIG = 46, B_WST = 47, B_QF = 48, B_ORB = 49, B_YSIG = 50,
  B_F0 = 51, B_FULL1 = 52
};
constexpr uint32_t OFF_EPOCH = OFF_BAR + 8 * 58, OFF_D = OFF_BAR + 8 * 60;
__device__ __forceinline__ uint32_t off_o(int j) { return j < 4 ? OFF_OA + j * O_BYTES : j < 6 ? OFF_CH0 + (j - 4) * O_BYTES : OFF_OA + (j - 6) * O_BYTES; }
__device__ __forceinline__ uint32_t off_w(int j) { return j < 4 ? OFF_WA + j * WO_BYTES : j == 4 ? OFF_KVX : j == 5 ? OFF_WC : OFF_WA + (j - 6) * WO_BYTES; }
__device__ __forceinline__ int step_src(int hg, int j) { return j == 0 ? hg : j <= hg ? j - 1 : j; }
__device__ __forceinline__ bool tail_first(int hg) { return (hg & 3) == 3; }
__device__ __forceinline__ uint32_t off_ch(int c) { return (c < 3 ? OFF_CH0 : OFF_CH3 - 3 * CH_BYTES) + c * CH_BYTES; }

#define U_PITCH 264
__device__ __align__(1024) uint4 g_U[DIM * U_PITCH];
__device__ uint4 g_O[NCTA * 1280];
__device__ uint4 g_WO[64 * 800];
__device__ uint4 g_halo[NCTA * 2 * 7 * 32];
__device__ __align__(128) float g_gate[SEQ];
__device__ unsigned g_cnt[32 * (1 + 2 * 16 + 8 + NCTA)];
constexpr int C_LAUNCH = 0, C_PREP = 32, C_Y = 32 * 17, C_W = 32 * 33, C_O = 32 * 41;

#define TSM(cond, slot) do { } while (0)
#define TSIF(cond, slot) do { if (__LINE__ >= FENCE_LO && __LINE__ < FENCE_HI) sched_fence(); } while (0)
__device__ __forceinline__ void sched_fence() {
  asm volatile("{\n.reg .pred p;\n.reg .u32 c;\nmov.u32 c, %%clock;\nsetp.eq.u32 p, c, 0;\n@p st.shared.u32 [%0], c;\n}"
               ::"r"(1024 + OFF_EPOCH + 4) : "memory");
}
#define TS(slot) TSIF(true, slot)

struct Params {
  const __nv_bfloat16 *q, *k, *v, *shift_k, *ssm_k, *ssm_D, *wqkv, *wo, *gate_w;
  __nv_bfloat16* out;
  uint32_t zero;
};

constexpr int SPIN_LIMIT = 1 << 17;

__device__ __forceinline__ void mbar_init(uint32_t bar, uint32_t count) {
  asm volatile("mbarrier.init.shared::cta.b64 [%0], %1;" ::"r"(bar), "r"(count) : "memory");
}
__device__ __forceinline__ void mbar_expect_tx(uint32_t bar, uint32_t bytes) {
  asm volatile("mbarrier.arrive.expect_tx.shared::cta.b64 _, [%0], %1;" ::"r"(bar), "r"(bytes) : "memory");
}
__device__ __forceinline__ void mbar_arrive(uint32_t bar) {
  asm volatile("mbarrier.arrive.shared::cta.b64 _, [%0];" ::"r"(bar) : "memory");
}
__device__ __forceinline__ void mbar_wait(uint32_t bar, uint32_t parity) {
  uint32_t ok;
  int spins = 0;
  do {
      asm volatile("{\n.reg .pred p;\nmbarrier.try_wait.parity.shared::cta.b64 p, [%1], %2;\nselp.b32 %0, 1, 0, p;\n}"
                   : "=r"(ok) : "r"(bar), "r"(parity) : "memory");
    if (++spins > SPIN_LIMIT) break;
  } while (!ok);
}
__device__ __forceinline__ unsigned flag_read(const unsigned* p) {
  unsigned v;
  asm volatile("ld.relaxed.gpu.global.u32 %0, [%1];" : "=r"(v) : "l"(p) : "memory");
  return v;
}
__device__ __forceinline__ void flag_poll(const unsigned* p, unsigned target) {
  unsigned v;
  int spins = 0;
  do {
    asm volatile("ld.relaxed.gpu.global.u32 %0, [%1];" : "=r"(v) : "l"(p) : "memory");
    if (++spins > SPIN_LIMIT) break;
  } while ((int)(v - target) < 0);
}
__device__ __forceinline__ void flag_wait(const unsigned* p, unsigned target) {
  flag_poll(p, target);
}
__device__ __forceinline__ void flag_signal(unsigned* p, int n, int lane) {
  if (lane == 0) asm volatile("fence.release.gpu;" ::: "memory");
  __syncwarp();
  if (lane < n) asm volatile("red.relaxed.gpu.global.add.u32 [%0], 1;" ::"l"(p + 32 * lane) : "memory");
}
__device__ __forceinline__ void flag_bump(unsigned* p) {
  asm volatile("red.relaxed.gpu.global.add.u32 [%0], 1;" ::"l"(p) : "memory");
}
__device__ __forceinline__ void fence_async_smem() { asm volatile("fence.proxy.async.shared::cta;" ::: "memory"); }
__device__ __forceinline__ void wg_sync(int id) { asm volatile("bar.sync %0, 128;" ::"r"(id) : "memory"); }

__device__ __forceinline__ void tma_2d(uint32_t dst, const CUtensorMap* tm, int c0, int c1, uint32_t bar) {
  asm volatile("cp.async.bulk.tensor.2d.shared::cluster.global.mbarrier::complete_tx::bytes [%0], [%1, {%3, %4}], [%2];"
               ::"r"(dst), "l"(tm), "r"(bar), "r"(c0), "r"(c1) : "memory");
}
__device__ __forceinline__ void tma_3d(uint32_t dst, const CUtensorMap* tm, int c0, int c1, int c2, uint32_t bar) {
  asm volatile("cp.async.bulk.tensor.3d.shared::cluster.global.mbarrier::complete_tx::bytes [%0], [%1, {%3, %4, %5}], [%2];"
               ::"r"(dst), "l"(tm), "r"(bar), "r"(c0), "r"(c1), "r"(c2) : "memory");
}
__device__ __forceinline__ void bulk_load(uint32_t dst, const void* src, uint32_t bytes, uint32_t bar) {
  asm volatile("cp.async.bulk.shared::cluster.global.mbarrier::complete_tx::bytes [%0], [%1], %2, [%3];"
               ::"r"(dst), "l"(src), "r"(bytes), "r"(bar) : "memory");
}
__device__ __forceinline__ void bulk_store(void* dst, uint32_t src, uint32_t bytes) {
  asm volatile("cp.async.bulk.global.shared::cta.bulk_group [%0], [%1], %2;" ::"l"(dst), "r"(src), "r"(bytes) : "memory");
}
__device__ __forceinline__ void bulk_wait_read() {
  asm volatile("cp.async.bulk.commit_group;\ncp.async.bulk.wait_group.read 0;" ::: "memory");
}

__device__ __forceinline__ void publish(void* dst, uint32_t src, uint32_t bytes, uint32_t bar) {
  bulk_store(dst, src, bytes);
  bulk_wait_read();
  bulk_load(src, dst, bytes, bar);
}

__device__ __forceinline__ void wg_fence() { asm volatile("wgmma.fence.sync.aligned;" ::: "memory"); }
__device__ __forceinline__ void wg_commit() { asm volatile("wgmma.commit_group.sync.aligned;" ::: "memory"); }
template <int N> __device__ __forceinline__ void wg_wait() { asm volatile("wgmma.wait_group.sync.aligned %0;" ::"n"(N) : "memory"); }
__device__ __forceinline__ uint32_t desc_lo(uint32_t addr, uint32_t lbo) { return ((addr & 0x3FFFF) >> 4) | ((lbo >> 4) << 16); }
constexpr uint32_t desc_hi(uint32_t sbo, uint32_t swz) { return (sbo >> 4) | (swz << 30); }
constexpr uint32_t HI_SW128 = desc_hi(1024, 1), HI_SW64 = desc_hi(512, 2), HI_SW32 = desc_hi(256, 3), HI_NONE = desc_hi(128, 0);
template <int N> __device__ __forceinline__ void pin(float* d) {
#pragma unroll
  for (int i = 0; i < N; i++) asm volatile("" : "+f"(d[i])::"memory");
}

__device__ __forceinline__ uint32_t lds32(uint32_t a) {
  uint32_t v;
  asm volatile("ld.volatile.shared.u32 %0, [%1];" : "=r"(v) : "r"(a) : "memory");
  return v;
}
__device__ __forceinline__ uint2 ldg64(const void* a) {
  uint2 v;
  asm volatile("ld.global.nc.v2.u32 {%0, %1}, [%2];" : "=r"(v.x), "=r"(v.y) : "l"(a) : "memory");
  return v;
}
__device__ __forceinline__ void ldsm4(uint32_t* r, uint32_t a) {
  asm volatile("ldmatrix.sync.aligned.m8n8.x4.shared.b16 {%0, %1, %2, %3}, [%4];"
               : "=r"(r[0]), "=r"(r[1]), "=r"(r[2]), "=r"(r[3]) : "r"(a) : "memory");
}
__device__ __forceinline__ void ldsm4t(uint32_t* r, uint32_t a) {
  asm volatile("ldmatrix.sync.aligned.m8n8.x4.trans.shared.b16 {%0, %1, %2, %3}, [%4];"
               : "=r"(r[0]), "=r"(r[1]), "=r"(r[2]), "=r"(r[3]) : "r"(a) : "memory");
}
__device__ __forceinline__ uint2 lds64(uint32_t a) {
  uint2 v;
  asm volatile("ld.shared.v2.u32 {%0, %1}, [%2];" : "=r"(v.x), "=r"(v.y) : "r"(a) : "memory");
  return v;
}
__device__ __forceinline__ uint4 lds128(uint32_t a) {
  uint4 v;
  asm volatile("ld.shared.v4.u32 {%0, %1, %2, %3}, [%4];" : "=r"(v.x), "=r"(v.y), "=r"(v.z), "=r"(v.w) : "r"(a) : "memory");
  return v;
}
__device__ __forceinline__ void sts128(uint32_t a, uint32_t x, uint32_t y, uint32_t z, uint32_t w) {
  asm volatile("st.shared.v4.u32 [%0], {%1, %2, %3, %4};" ::"r"(a), "r"(x), "r"(y), "r"(z), "r"(w) : "memory");
}
__device__ __forceinline__ void stsm4(uint32_t a, const uint32_t* r) {
  asm volatile("stmatrix.sync.aligned.m8n8.x4.shared.b16 [%0], {%1, %2, %3, %4};" ::"r"(a), "r"(r[0]), "r"(r[1]), "r"(r[2]), "r"(r[3]) : "memory");
}
__device__ __forceinline__ uint32_t pack2(float lo, float hi) {
  uint32_t r;
  asm("cvt.rn.bf16x2.f32 %0, %1, %2;" : "=r"(r) : "f"(hi), "f"(lo));
  return r;
}
__device__ __forceinline__ uint32_t movm(uint32_t a) {
  uint32_t d;
  asm volatile("movmatrix.sync.aligned.m8n8.trans.b16 %0, %1;" : "=r"(d) : "r"(a));
  return d;
}
__device__ __forceinline__ uint32_t bmul(uint32_t a, uint32_t b) {
  uint32_t d;
  asm("mul.rn.bf16x2 %0, %1, %2;" : "=r"(d) : "r"(a), "r"(b));
  return d;
}
__device__ __forceinline__ uint32_t badd(uint32_t a, uint32_t b) {
  uint32_t d;
  asm("add.rn.bf16x2 %0, %1, %2;" : "=r"(d) : "r"(a), "r"(b));
  return d;
}
__device__ __forceinline__ uint32_t bfma(uint32_t a, uint32_t b, uint32_t c) {
  uint32_t d;
  asm("fma.rn.bf16x2 %0, %1, %2, %3;" : "=r"(d) : "r"(a), "r"(b), "r"(c));
  return d;
}
__device__ __forceinline__ float bf_lo(uint32_t x) { return __uint_as_float(x << 16); }
__device__ __forceinline__ float bf_hi(uint32_t x) { return __uint_as_float(x & 0xFFFF0000u); }
__device__ __forceinline__ float ex2(float x) {
  float y;
  asm("ex2.approx.ftz.f32 %0, %1;" : "=f"(y) : "f"(x));
  return y;
}
__device__ __forceinline__ float rcp(float x) {
  float y;
  asm("rcp.approx.ftz.f32 %0, %1;" : "=f"(y) : "f"(x));
  return y;
}
__device__ __forceinline__ void mma16816(float* d, uint32_t a0, uint32_t a1, uint32_t a2, uint32_t a3, uint32_t b0, uint32_t b1) {
  asm volatile("mma.sync.aligned.m16n8k16.row.col.f32.bf16.bf16.f32 {%0, %1, %2, %3}, {%4, %5, %6, %7}, {%8, %9}, {%0, %1, %2, %3};"
               : "+f"(d[0]), "+f"(d[1]), "+f"(d[2]), "+f"(d[3])
               : "r"(a0), "r"(a1), "r"(a2), "r"(a3), "r"(b0), "r"(b1));
}
__device__ __forceinline__ void mma1688(float* d, uint32_t a0, uint32_t a1, uint32_t b0) {
  asm volatile("mma.sync.aligned.m16n8k8.row.col.f32.bf16.bf16.f32 {%0, %1, %2, %3}, {%4, %5}, {%6}, {%0, %1, %2, %3};"
               : "+f"(d[0]), "+f"(d[1]), "+f"(d[2]), "+f"(d[3])
               : "r"(a0), "r"(a1), "r"(b0));
}

template <int N> struct WgRS;
template <int N> struct WgSST;
template <> struct WgRS<32> {
  template <uint32_t HB>
  static __device__ __forceinline__ void mma(float* d, const uint32_t* a, uint32_t db) {
    asm volatile("{\n.reg .pred p;\n.reg .b64 db;\nsetp.ne.b32 p, %22, 0;\n"
      "mov.b64 db, {%20, %21};\n"
      "wgmma.mma_async.sync.aligned.m64n32k16.f32.bf16.bf16 {"
      "%0, %1, %2, %3, %4, %5, %6, %7, %8, %9, %10, %11, %12, %13, %14, %15"
      "}, {%16, %17, %18, %19}, db, p, 1, 1, 1;\n}\n"
      : "+f"(d[0]), "+f"(d[1]), "+f"(d[2]), "+f"(d[3]), "+f"(d[4]), "+f"(d[5]), "+f"(d[6]), "+f"(d[7]),
        "+f"(d[8]), "+f"(d[9]), "+f"(d[10]), "+f"(d[11]), "+f"(d[12]), "+f"(d[13]), "+f"(d[14]), "+f"(d[15])
      : "r"(a[0]), "r"(a[1]), "r"(a[2]), "r"(a[3]), "r"(db), "n"(HB), "n"(1));
  }
  template <uint32_t HB>
  static __device__ __forceinline__ void set(float* d, const uint32_t* a, uint32_t db) {
    asm volatile("{\n.reg .pred p;\n.reg .b64 db;\nsetp.ne.b32 p, %22, 0;\n"
      "mov.b64 db, {%20, %21};\n"
      "wgmma.mma_async.sync.aligned.m64n32k16.f32.bf16.bf16 {"
      "%0, %1, %2, %3, %4, %5, %6, %7, %8, %9, %10, %11, %12, %13, %14, %15"
      "}, {%16, %17, %18, %19}, db, p, 1, 1, 1;\n}\n"
      : "=f"(d[0]), "=f"(d[1]), "=f"(d[2]), "=f"(d[3]), "=f"(d[4]), "=f"(d[5]), "=f"(d[6]), "=f"(d[7]),
        "=f"(d[8]), "=f"(d[9]), "=f"(d[10]), "=f"(d[11]), "=f"(d[12]), "=f"(d[13]), "=f"(d[14]), "=f"(d[15])
      : "r"(a[0]), "r"(a[1]), "r"(a[2]), "r"(a[3]), "r"(db), "n"(HB), "n"(0));
  }
};
template <> struct WgRS<64> {
  template <uint32_t HB>
  static __device__ __forceinline__ void mma(float* d, const uint32_t* a, uint32_t db) {
    asm volatile("{\n.reg .pred p;\n.reg .b64 db;\nsetp.ne.b32 p, %38, 0;\n"
      "mov.b64 db, {%36, %37};\n"
      "wgmma.mma_async.sync.aligned.m64n64k16.f32.bf16.bf16 {"
      "%0, %1, %2, %3, %4, %5, %6, %7, %8, %9, %10, %11, %12, %13, %14, %15, "
      "%16, %17, %18, %19, %20, %21, %22, %23, %24, %25, %26, %27, %28, %29, %30, %31"
      "}, {%32, %33, %34, %35}, db, p, 1, 1, 1;\n}\n"
      : "+f"(d[0]), "+f"(d[1]), "+f"(d[2]), "+f"(d[3]), "+f"(d[4]), "+f"(d[5]), "+f"(d[6]), "+f"(d[7]),
        "+f"(d[8]), "+f"(d[9]), "+f"(d[10]), "+f"(d[11]), "+f"(d[12]), "+f"(d[13]), "+f"(d[14]), "+f"(d[15]),
        "+f"(d[16]), "+f"(d[17]), "+f"(d[18]), "+f"(d[19]), "+f"(d[20]), "+f"(d[21]), "+f"(d[22]), "+f"(d[23]),
        "+f"(d[24]), "+f"(d[25]), "+f"(d[26]), "+f"(d[27]), "+f"(d[28]), "+f"(d[29]), "+f"(d[30]), "+f"(d[31])
      : "r"(a[0]), "r"(a[1]), "r"(a[2]), "r"(a[3]), "r"(db), "n"(HB), "n"(1));
  }
  template <uint32_t HB>
  static __device__ __forceinline__ void set(float* d, const uint32_t* a, uint32_t db) {
    asm volatile("{\n.reg .pred p;\n.reg .b64 db;\nsetp.ne.b32 p, %38, 0;\n"
      "mov.b64 db, {%36, %37};\n"
      "wgmma.mma_async.sync.aligned.m64n64k16.f32.bf16.bf16 {"
      "%0, %1, %2, %3, %4, %5, %6, %7, %8, %9, %10, %11, %12, %13, %14, %15, "
      "%16, %17, %18, %19, %20, %21, %22, %23, %24, %25, %26, %27, %28, %29, %30, %31"
      "}, {%32, %33, %34, %35}, db, p, 1, 1, 1;\n}\n"
      : "=f"(d[0]), "=f"(d[1]), "=f"(d[2]), "=f"(d[3]), "=f"(d[4]), "=f"(d[5]), "=f"(d[6]), "=f"(d[7]),
        "=f"(d[8]), "=f"(d[9]), "=f"(d[10]), "=f"(d[11]), "=f"(d[12]), "=f"(d[13]), "=f"(d[14]), "=f"(d[15]),
        "=f"(d[16]), "=f"(d[17]), "=f"(d[18]), "=f"(d[19]), "=f"(d[20]), "=f"(d[21]), "=f"(d[22]), "=f"(d[23]),
        "=f"(d[24]), "=f"(d[25]), "=f"(d[26]), "=f"(d[27]), "=f"(d[28]), "=f"(d[29]), "=f"(d[30]), "=f"(d[31])
      : "r"(a[0]), "r"(a[1]), "r"(a[2]), "r"(a[3]), "r"(db), "n"(HB), "n"(0));
  }
};
template <> struct WgSST<48> {
  template <uint32_t HA, uint32_t HB>
  static __device__ __forceinline__ void mma(float* d, uint32_t da, uint32_t db, int sc) {
    asm volatile("{\n.reg .pred p;\n.reg .b64 da, db;\nsetp.ne.b32 p, %28, 0;\n"
      "mov.b64 da, {%24, %25};\nmov.b64 db, {%26, %27};\n"
      "wgmma.mma_async.sync.aligned.m64n48k16.f32.bf16.bf16 {"
      "%0, %1, %2, %3, %4, %5, %6, %7, %8, %9, %10, %11, %12, %13, %14, %15, "
      "%16, %17, %18, %19, %20, %21, %22, %23"
      "}, da, db, p, 1, 1, 0, 1;\n}\n"
      : "+f"(d[0]), "+f"(d[1]), "+f"(d[2]), "+f"(d[3]), "+f"(d[4]), "+f"(d[5]), "+f"(d[6]), "+f"(d[7]),
        "+f"(d[8]), "+f"(d[9]), "+f"(d[10]), "+f"(d[11]), "+f"(d[12]), "+f"(d[13]), "+f"(d[14]), "+f"(d[15]),
        "+f"(d[16]), "+f"(d[17]), "+f"(d[18]), "+f"(d[19]), "+f"(d[20]), "+f"(d[21]), "+f"(d[22]), "+f"(d[23])
      : "r"(da), "n"(HA), "r"(db), "n"(HB), "r"(sc));
  }
};
template <> struct WgSST<80> {
  template <uint32_t HA, uint32_t HB>
  static __device__ __forceinline__ void mma(float* d, uint32_t da, uint32_t db, int sc) {
    asm volatile("{\n.reg .pred p;\n.reg .b64 da, db;\nsetp.ne.b32 p, %44, 0;\n"
      "mov.b64 da, {%40, %41};\nmov.b64 db, {%42, %43};\n"
      "wgmma.mma_async.sync.aligned.m64n80k16.f32.bf16.bf16 {"
      "%0, %1, %2, %3, %4, %5, %6, %7, %8, %9, %10, %11, %12, %13, %14, %15, "
      "%16, %17, %18, %19, %20, %21, %22, %23, %24, %25, %26, %27, %28, %29, %30, %31, "
      "%32, %33, %34, %35, %36, %37, %38, %39"
      "}, da, db, p, 1, 1, 0, 1;\n}\n"
      : "+f"(d[0]), "+f"(d[1]), "+f"(d[2]), "+f"(d[3]), "+f"(d[4]), "+f"(d[5]), "+f"(d[6]), "+f"(d[7]),
        "+f"(d[8]), "+f"(d[9]), "+f"(d[10]), "+f"(d[11]), "+f"(d[12]), "+f"(d[13]), "+f"(d[14]), "+f"(d[15]),
        "+f"(d[16]), "+f"(d[17]), "+f"(d[18]), "+f"(d[19]), "+f"(d[20]), "+f"(d[21]), "+f"(d[22]), "+f"(d[23]),
        "+f"(d[24]), "+f"(d[25]), "+f"(d[26]), "+f"(d[27]), "+f"(d[28]), "+f"(d[29]), "+f"(d[30]), "+f"(d[31]),
        "+f"(d[32]), "+f"(d[33]), "+f"(d[34]), "+f"(d[35]), "+f"(d[36]), "+f"(d[37]), "+f"(d[38]), "+f"(d[39])
      : "r"(da), "n"(HA), "r"(db), "n"(HB), "r"(sc));
  }
};
template <> struct WgSST<192> {
  template <uint32_t HA, uint32_t HB>
  static __device__ __forceinline__ void mma(float* d, uint32_t da, uint32_t db, int sc) {
    asm volatile("{\n.reg .pred p;\n.reg .b64 da, db;\nsetp.ne.b32 p, %100, 0;\n"
      "mov.b64 da, {%96, %97};\nmov.b64 db, {%98, %99};\n"
      "wgmma.mma_async.sync.aligned.m64n192k16.f32.bf16.bf16 {"
      "%0, %1, %2, %3, %4, %5, %6, %7, %8, %9, %10, %11, %12, %13, %14, %15, "
      "%16, %17, %18, %19, %20, %21, %22, %23, %24, %25, %26, %27, %28, %29, %30, %31, "
      "%32, %33, %34, %35, %36, %37, %38, %39, %40, %41, %42, %43, %44, %45, %46, %47, "
      "%48, %49, %50, %51, %52, %53, %54, %55, %56, %57, %58, %59, %60, %61, %62, %63, "
      "%64, %65, %66, %67, %68, %69, %70, %71, %72, %73, %74, %75, %76, %77, %78, %79, "
      "%80, %81, %82, %83, %84, %85, %86, %87, %88, %89, %90, %91, %92, %93, %94, %95"
      "}, da, db, p, 1, 1, 0, 1;\n}\n"
      : "+f"(d[0]), "+f"(d[1]), "+f"(d[2]), "+f"(d[3]), "+f"(d[4]), "+f"(d[5]), "+f"(d[6]), "+f"(d[7]),
        "+f"(d[8]), "+f"(d[9]), "+f"(d[10]), "+f"(d[11]), "+f"(d[12]), "+f"(d[13]), "+f"(d[14]), "+f"(d[15]),
        "+f"(d[16]), "+f"(d[17]), "+f"(d[18]), "+f"(d[19]), "+f"(d[20]), "+f"(d[21]), "+f"(d[22]), "+f"(d[23]),
        "+f"(d[24]), "+f"(d[25]), "+f"(d[26]), "+f"(d[27]), "+f"(d[28]), "+f"(d[29]), "+f"(d[30]), "+f"(d[31]),
        "+f"(d[32]), "+f"(d[33]), "+f"(d[34]), "+f"(d[35]), "+f"(d[36]), "+f"(d[37]), "+f"(d[38]), "+f"(d[39]),
        "+f"(d[40]), "+f"(d[41]), "+f"(d[42]), "+f"(d[43]), "+f"(d[44]), "+f"(d[45]), "+f"(d[46]), "+f"(d[47]),
        "+f"(d[48]), "+f"(d[49]), "+f"(d[50]), "+f"(d[51]), "+f"(d[52]), "+f"(d[53]), "+f"(d[54]), "+f"(d[55]),
        "+f"(d[56]), "+f"(d[57]), "+f"(d[58]), "+f"(d[59]), "+f"(d[60]), "+f"(d[61]), "+f"(d[62]), "+f"(d[63]),
        "+f"(d[64]), "+f"(d[65]), "+f"(d[66]), "+f"(d[67]), "+f"(d[68]), "+f"(d[69]), "+f"(d[70]), "+f"(d[71]),
        "+f"(d[72]), "+f"(d[73]), "+f"(d[74]), "+f"(d[75]), "+f"(d[76]), "+f"(d[77]), "+f"(d[78]), "+f"(d[79]),
        "+f"(d[80]), "+f"(d[81]), "+f"(d[82]), "+f"(d[83]), "+f"(d[84]), "+f"(d[85]), "+f"(d[86]), "+f"(d[87]),
        "+f"(d[88]), "+f"(d[89]), "+f"(d[90]), "+f"(d[91]), "+f"(d[92]), "+f"(d[93]), "+f"(d[94]), "+f"(d[95])
      : "r"(da), "n"(HA), "r"(db), "n"(HB), "r"(sc));
  }
};

struct FftConst {
  uint32_t f[2][4], fi[4][4];
  uint32_t ta[2][2], tb[2][2];
};
__device__ __forceinline__ void cis(int m, float scale, float& c, float& s) {
  const float a = (float)m * (-6.283185307179586f * scale);
  c = __cosf(a);
  s = __sinf(a);
}
__device__ __forceinline__ void fft_tables(uint32_t (&v)[12], int tw) {
  const int row = tw >> 2, ch = tw & 3;
#pragma unroll
  for (int i = 0; i < 4; i++) {
    float c[2], s[2], x[2];
#pragma unroll
    for (int e = 0; e < 2; e++) {
      cis((((32 * (8 * ch + 2 * i + e) + 15) * (4 * row - 63) + 2048) & 4095) - 2048, 1.f / 4096, c[e], s[e]);
      float gc, gs;
      cis((((row & 15) * (8 * (ch & 1) + 2 * i + e) + 8) & 15) - 8, 1.f / 16, gc, gs);
      x[e] = (row >> 4) == (ch >> 1) ? gc : (ch >> 1) ? gs : -gs;
    }
    v[i] = pack2(c[0] * 0.125f, c[1] * 0.125f);
    v[4 + i] = pack2(s[0] * 0.125f, s[1] * 0.125f);
    v[8 + i] = pack2(x[0], x[1]);
  }
#pragma unroll
  for (int i = 0; i < 12; i++) asm volatile("" : "+r"(v[i]));
}
__device__ __forceinline__ void fft_tables_store(const uint32_t (&v)[12], uint32_t sb, int tw) {
  const int row = tw >> 2;
  const uint32_t x = ((tw ^ (row >> 1)) & 3) << 4, a = sb + OFF_FT + (16 * (row >> 3) + (row & 7)) * 64 + x;
  sts128(a, v[0], v[1], v[2], v[3]);
  sts128(a + 512, v[4], v[5], v[6], v[7]);
  sts128(sb + OFF_GT + row * 64 + x, v[8], v[9], v[10], v[11]);
}
__device__ __forceinline__ void fft_twiddles(uint32_t (&v)[2], int tw) {
  float a[2], s[2];
#pragma unroll
  for (int i = 0; i < 2; i++) {
    float c;
    cis((2 * (2 * (tw & 3) + i) - 15) * (4 * (tw >> 2) - 63), 1.f / 4096, c, s[i]);
    a[i] = __fdividef(-s[i], 1.f + c);
  }
  v[0] = pack2(a[0], a[1]);
  v[1] = pack2(s[0], s[1]);
  asm volatile("" : "+r"(v[0]), "+r"(v[1]));
}
__device__ __forceinline__ void fft_matrices(FftConst& k, uint32_t sb, int w, int lane) {
  const uint32_t x = (lane >> 1) & 3;
  const uint2 t0 = lds64(sb + OFF_TT + 256 * w + 8 * lane), t1 = lds64(sb + OFF_TT + 256 * w + 8 * (lane ^ 3));
  k.ta[0][0] = t0.x;
  k.tb[0][0] = t0.y;
  k.ta[1][1] = __byte_perm(t1.x, 0, 0x1032);
  k.tb[1][1] = __byte_perm(t1.y, 0, 0x1032);
#pragma unroll
  for (int j = 0; j < 2; j++) {
    k.ta[1 - j][j] = k.ta[j][j] ^ 0x80008000u;
    k.tb[1 - j][j] = k.tb[j][j] ^ 0x80008000u;
    asm volatile("" : "+r"(k.ta[0][j]), "+r"(k.tb[0][j]), "+r"(k.ta[1][j]), "+r"(k.tb[1][j]));
  }
#pragma unroll
  for (int i = 0; i < 2; i++) {
    ldsm4(k.f[i], sb + OFF_FT + (16 * w + (lane & 15)) * 64 + (((2 * i + (lane >> 4)) ^ x) << 4));
    ldsm4t(k.fi[i], sb + OFF_FT + (32 * i + lane) * 64 + ((w ^ x) << 4));
#pragma unroll
    for (int j = 0; j < 4; j++) {
      k.fi[2 + i][j] = (j & 1) ? k.fi[i][j - 1] ^ 0x80008000u : k.fi[i][j + 1];
      asm volatile("" : "+r"(k.fi[2 + i][j]));
    }
  }
}
__device__ __forceinline__ void rot(uint32_t& x, uint32_t& y, uint32_t a, uint32_t b) {
  x = bfma(a, y, x);
  y = bfma(b, x, y);
  x = bfma(a, y, x);
}
__device__ __forceinline__ void twiddle_fwd(uint32_t (&a)[4][4], float* d, const FftConst& k) {
#pragma unroll
  for (int q = 0; q < 4; q++)
#pragma unroll
    for (int j = 0; j < 2; j++) {
      const float* x = d + 8 * q + 4 * j;
      uint32_t re = pack2(x[0], x[1]), im = pack2(x[2], x[3]);
      rot(re, im, k.ta[0][j], k.tb[0][j]);
      a[q & 2][2 * j + (q & 1)] = re;
      a[(q & 2) + 1][2 * j + (q & 1)] = im;
    }
}
__device__ __forceinline__ void g_step(float* d, const uint32_t (&a)[4][4], uint32_t dre, uint32_t dim) {
  WgRS<32>::set<HI_SW64>(d, a[0], dre);
  WgRS<32>::set<HI_SW64>(d + 16, a[2], dre);
  WgRS<32>::mma<HI_SW64>(d, a[1], dim);
  WgRS<32>::mma<HI_SW64>(d + 16, a[3], dim);
  wg_commit();
}

__device__ __forceinline__ void products(uint32_t (&a)[4][4], const float* H, const float* U, int p) {
#pragma unroll
  for (int j = 0; j < 2; j++)
#pragma unroll
    for (int m = 2 * p; m < 2 * p + 2; m++) {
      float pr[2], pi[2];
#pragma unroll
      for (int x = 0; x < 2; x++)
#pragma unroll
        for (int q = 0; q <= m; q++) {
          const int ih = 16 * (q >> 1) + 2 * (q & 1) + 4 * j + x, iu = 16 * ((m - q) >> 1) + 2 * ((m - q) & 1) + 4 * j + x;
          pr[x] = q ? fmaf(H[ih], U[iu], pr[x]) : H[ih] * U[iu];
          pi[x] = q ? fmaf(H[ih], U[iu + 8], pi[x]) : H[ih] * U[iu + 8];
          pr[x] = fmaf(-H[ih + 8], U[iu + 8], pr[x]);
          pi[x] = fmaf(H[ih + 8], U[iu], pi[x]);
        }
      a[m & 2][2 * j + (m & 1)] = pack2(pr[0], pr[1]);
      a[(m & 2) + 1][2 * j + (m & 1)] = pack2(pi[0], pi[1]);
    }
}

__device__ __forceinline__ void conv_channel(const FftConst& k, uint32_t sb, int c, int wg, int w, int lane) {
  const uint32_t cb = sb + off_ch(c), bars = sb + OFF_BAR;
  const uint32_t du = desc_lo(cb, 1024), dg = desc_lo(sb + OFF_GT, 16), dz = desc_lo(cb + U_BYTES, 16);
  float U[32], H[32];
  uint32_t a[4][4], e[4][4];
  const float dv = __uint_as_float(lds32(sb + OFF_D + 4 * c));
  wg_fence();
  WgRS<64>::set<HI_SW32>(H, k.f[0], du + 256);
  WgRS<64>::mma<HI_SW32>(H, k.f[1], du + 256 + 32);
  wg_commit();
  wg_wait<0>();
  pin<32>(H);
  twiddle_fwd(a, H, k);
  mbar_wait(bars + 8 * (B_U + (c < 3 ? c : 3)), 0);
  TSM(w == 0 && c < 3, 7 + wg);
  wg_fence();
  WgRS<64>::set<HI_SW32>(U, k.f[0], du);
  WgRS<64>::mma<HI_SW32>(U, k.f[1], du + 32);
  wg_commit();
  g_step(H, a, dg, dg + 64);
  wg_wait<1>();
  pin<32>(U);
  twiddle_fwd(e, U, k);
  wg_fence();
  g_step(U, e, dg, dg + 64);
  wg_wait<0>();
  pin<32>(U);
  pin<32>(H);
#pragma unroll
  for (int j = 0; j < 4; j++) H[4 * (j >> 1) + (j & 1)] += dv;
  float V[32];
#pragma unroll
  for (int p = 0; p < 2; p++) {
    products(a, H, U, p);
    wg_fence();
    WgRS<32>::set<HI_SW64>(V + 16 * p, a[2 * p], dg + 64);
    WgRS<32>::mma<HI_SW64>(V + 16 * p, a[2 * p + 1], dg);
    wg_commit();
  }
  const uint32_t za = cb + U_BYTES + (8 * w + (lane & 7)) * 128 + (((lane >> 3) ^ (lane & 7)) << 4);
  const uint32_t ya = cb + (lane >> 4) * 1024 + (8 * w + (lane & 7)) * 32 + ((((lane >> 3) ^ (lane >> 2)) & 1) << 4);
  wg_sync(1 + wg);
#pragma unroll
  for (int p = 0; p < 2; p++) {
    if (p == 0) wg_wait<1>();
    else wg_wait<0>();
    pin<16>(V + 16 * p);
#pragma unroll
    for (int i = 0; i < 4; i++) {
      const int j = i & 1;
      const float* x = V + 16 * p + 4 * j + (i & 2);
      e[p][i] = pack2(x[8], x[9]);
      e[2 + p][i] = pack2(x[0], x[1]);
      rot(e[p][i], e[2 + p][i], k.ta[1][j], k.tb[1][j]);
    }
    stsm4(za ^ (64 * p), e[p]);
    stsm4((za ^ (64 * p)) + 4096, e[2 + p]);
  }
  fence_async_smem();
  wg_sync(1 + wg);
  wg_fence();
  WgRS<64>::set<HI_SW128>(H, k.fi[0], dz);
#pragma unroll
  for (int ks = 1; ks < 4; ks++) WgRS<64>::mma<HI_SW128>(H, k.fi[ks], dz + 128 * ks);
  wg_commit();
  wg_wait<0>();
  pin<32>(H);
  if (lane == 0) mbar_arrive(bars + 8 * B_CVD);
  TSIF(w == 0, 88 + c);
#pragma unroll
  for (int j = 0; j < 8; j++)
    a[j >> 2][j & 3] = j < 2 ? pack2(H[4 * j], H[4 * j + 1]) : pack2(H[4 * j] + H[4 * j - 6], H[4 * j + 1] + H[4 * j - 5]);
  stsm4(ya, a[0]);
  stsm4(ya + 2048, a[1]);
  fence_async_smem();
  __syncwarp();
}

__device__ __forceinline__ void prep_slab(uint4* res, const uint2* sw, uint32_t sb, int slab, int w, int lane) {
  const int t = lane & 3, tp = (lane & 7) >> 1, pos = 8 * tp + 2 * (((lane >> 3) + tp) & 3) + (lane & 1);
  const uint32_t base = sb + OFF_KVS + slab * KVS_BYTES + pos * 128;
  uint32_t kk[2][4][4], vv[2][4];
  mbar_wait(sb + OFF_BAR + 8 * (B_KV + slab), 0);
#pragma unroll
  for (int h = 0; h < 2; h++) {
#pragma unroll
    for (int j = 0; j < 4; j++) {
      const uint32_t a = base + 128 * j;
      ldsm4t(kk[h][j], a + (((w + 4 * h) ^ ((a >> 7) & 7)) << 4));
    }
    const uint32_t a = base + KVS_V;
    ldsm4t(vv[h], a + (((w + 4 * h) ^ ((a >> 7) & 7)) << 4));
  }
#pragma unroll
  for (int h = 0; h < 2; h++) {
    uint32_t (&k)[4][4] = kk[h];
    uint32_t (&v)[4] = vv[h];
    const uint32_t w0 = __byte_perm(sw[h].x, 0, 0x1010), w1 = __byte_perm(sw[h].x, 0, 0x3232);
    const uint32_t w2 = __byte_perm(sw[h].y, 0, 0x1010), w3 = __byte_perm(sw[h].y, 0, 0x3232);
#pragma unroll
    for (int m = 0; m < 4; m++)
      v[m] = bmul(badd(badd(badd(bmul(k[0][m], w3), bmul(k[1][m], w2)), bmul(k[2][m], w1)), bmul(k[3][m], w0)), v[m]);
    uint32_t a[4];
#pragma unroll
    for (int m = 0; m < 4; m++) a[m] = (t & 1) ? v[(m + 3) & 3] : v[m];
    res[h] = (t & 2) ? make_uint4(a[2], a[3], a[0], a[1]) : make_uint4(a[0], a[1], a[2], a[3]);
  }
}

__device__ __forceinline__ void prep_gate(const Params& p, uint32_t sb, int b, int w, int lane) {
  uint2 gw[5], x[4][5];
#pragma unroll
  for (int j = 0; j < 5; j++) gw[j] = ldg64(reinterpret_cast<const uint2*>(p.gate_w) + lane + 32 * j);
#pragma unroll
  for (int i = 0; i < 4; i++)
#pragma unroll
    for (int j = 0; j < 5; j++)
      x[i][j] = ldg64(reinterpret_cast<const uint2*>(p.q) + (16 * b + 4 * w + i) * (DIM / 4) + lane + 32 * j);
  float s[4];
#pragma unroll
  for (int i = 0; i < 4; i++) {
    s[i] = 0.f;
#pragma unroll
    for (int j = 0; j < 5; j++) {
      const uint32_t m0 = bmul(x[i][j].x, gw[j].x), m1 = bmul(x[i][j].y, gw[j].y);
      s[i] += (bf_lo(m0) + bf_hi(m0)) + (bf_lo(m1) + bf_hi(m1));
    }
  }
  const bool h = lane & 16, q = lane & 8;
  const float a = (h ? s[2] : s[0]) + __shfl_xor_sync(0xffffffffu, h ? s[0] : s[2], 16);
  const float c = (h ? s[3] : s[1]) + __shfl_xor_sync(0xffffffffu, h ? s[1] : s[3], 16);
  float z = (q ? c : a) + __shfl_xor_sync(0xffffffffu, q ? a : c, 8);
#pragma unroll
  for (int o = 4; o > 0; o >>= 1) z += __shfl_xor_sync(0xffffffffu, z, o);
  z = bf_lo(pack2(z, 0.f));
  z = bf_lo(pack2(__fdividef(1.f, 1.f + __expf(-z)), 0.f));
  mbar_wait(sb + OFF_BAR + 8 * B_S3, 0);
  if ((lane & 7) == 0) asm volatile("st.shared.f32 [%0], %1;" ::"r"(sb + OFF_GATE + 64 * (b & 7) + 16 * w + (lane >> 1)), "f"(z) : "memory");
  fence_async_smem();
}

__device__ __forceinline__ uint32_t bmax(uint32_t a, uint32_t b) {
  uint32_t d;
  asm("max.bf16x2 %0, %1, %2;" : "=r"(d) : "r"(a), "r"(b));
  return d;
}
__device__ __forceinline__ void softmax_two(const float (&l)[2][2], uint32_t& p0, uint32_t& p1) {
  constexpr float kScale = 0.22360679774997896f, kLog2e = 1.4426950408889634f;
  const uint32_t r0 = pack2(l[0][0], l[1][0]), r1 = pack2(l[0][1], l[1][1]);
  const uint32_t x0 = pack2(bf_lo(r0) * kScale, bf_hi(r0) * kScale), x1 = pack2(bf_lo(r1) * kScale, bf_hi(r1) * kScale);
  uint32_t m = bmax(x0, x1);
  m = bmax(m, __shfl_xor_sync(0xffffffffu, m, 1));
  m = bmax(m, __shfl_xor_sync(0xffffffffu, m, 2));
  const float m0 = bf_lo(m) * kLog2e, m1 = bf_hi(m) * kLog2e;
  p0 = pack2(ex2(bf_lo(x0) * kLog2e - m0), ex2(bf_lo(x1) * kLog2e - m0));
  p1 = pack2(ex2(bf_hi(x0) * kLog2e - m1), ex2(bf_hi(x1) * kLog2e - m1));
}

__device__ __forceinline__ void halo_read(uint32_t (&kpv)[10], uint32_t (&vpv)[10], uint32_t (&tg)[7], const uint4* hp) {
#pragma unroll
  for (int j = 0; j < 7; j++) {
    uint32_t x0, x1, x2;
    asm volatile("ld.relaxed.gpu.global.v4.u32 {%0, %1, %2, %3}, [%4];"
                 : "=r"(x0), "=r"(x1), "=r"(x2), "=r"(tg[j]) : "l"(hp + 32 * j) : "memory");
    if (j < 4) kpv[3 * j] = x0; else vpv[3 * j - 10] = x0;
    if (j < 3) kpv[3 * j + 1] = x1; else vpv[3 * j - 9] = x1;
    if (j < 3) kpv[3 * j + 2] = x2; else if (j < 6) vpv[3 * j - 8] = x2;
  }
}

template <int ROT>
__device__ __forceinline__ void pack_qkv(const float* acc, uint32_t (&qlo)[10], uint32_t (&qhi)[10], uint32_t (&klo)[10],
                                         uint32_t (&khi)[10], uint32_t (&vlo)[10], uint32_t (&vhi)[10]) {
#pragma unroll
  for (int j = 0; j < 10; j++) {
    const int x = (j + ROT) % 10, tq = x < 8 ? x : 16 + x, tk = x < 8 ? 8 + x : 18 + x, tv = x < 8 ? 16 + x : 20 + x;
    khi[j] = pack2(acc[4 * tk + 2], acc[4 * tk + 3]);
    vhi[j] = movm(pack2(acc[4 * tv + 2], acc[4 * tv + 3]));
    qlo[j] = pack2(acc[4 * tq], acc[4 * tq + 1]);
    qhi[j] = pack2(acc[4 * tq + 2], acc[4 * tq + 3]);
    klo[j] = pack2(acc[4 * tk], acc[4 * tk + 1]);
    vlo[j] = pack2(acc[4 * tv], acc[4 * tv + 1]);
    asm volatile("" : "+r"(khi[j]), "+r"(qlo[j]), "+r"(qhi[j]), "+r"(klo[j]), "+r"(vlo[j]));
  }
}

template <int ROT> __device__ __forceinline__ void halo_send(const float* acc, uint4* ho, uint32_t tag) {
#pragma unroll
  for (int j = 0; j < 7; j++) {
    uint32_t x[3];
#pragma unroll
    for (int e = 0; e < 3; e++) {
      const int i = 3 * j + e, y = (i % 10 + ROT) % 10, tk = y < 8 ? 8 + y : 18 + y, tv = y < 8 ? 16 + y : 20 + y;
      x[e] = i < 10 ? pack2(acc[4 * tk + 2], acc[4 * tk + 3]) : i < 20 ? movm(pack2(acc[4 * tv + 2], acc[4 * tv + 3])) : 0u;
    }
    asm volatile("st.relaxed.gpu.global.v4.u32 [%0], {%1, %2, %3, %4};" ::"l"(ho + 32 * j), "r"(x[0]), "r"(x[1]), "r"(x[2]), "r"(tag) : "memory");
  }
}

__device__ __forceinline__ void attention(float* acc, uint32_t sb, int b, int par, int w, int lane, uint32_t tag) {
  const int g = lane >> 2, t = lane & 3;
  uint32_t klo[10], khi[10], vlo[10], vhi[10], qlo[10], qhi[10], kpv[10], vpv[10];
  if (w == 3 && b < NCTA - 8) {
    uint4* ho = g_halo + (b * 2 + par) * 224 + lane;
    if (tail_first(b & 7)) halo_send<8>(acc, ho, tag);
    else halo_send<0>(acc, ho, tag);
    TSIF(par == 0, 76);
    pin<120>(acc);
  }
  if (tail_first(b & 7)) pack_qkv<8>(acc, qlo, qhi, klo, khi, vlo, vhi);
  else pack_qkv<0>(acc, qlo, qhi, klo, khi, vlo, vhi);
  const uint32_t xa = sb + OFF_KVX + (par * 3) * 2560 + lane * 16;
  if (w < 3) {
    sts128(xa + w * 2560, khi[0], khi[1], khi[2], khi[3]);
    sts128(xa + w * 2560 + 512, khi[4], khi[5], khi[6], khi[7]);
    sts128(xa + w * 2560 + 1024, khi[8], khi[9], vhi[0], vhi[1]);
    sts128(xa + w * 2560 + 1536, vhi[2], vhi[3], vhi[4], vhi[5]);
    sts128(xa + w * 2560 + 2048, vhi[6], vhi[7], vhi[8], vhi[9]);
  }
  TSIF(par == 0 && w == 1, 64);
#pragma unroll
  for (int j = 0; j < 10; j++) vlo[j] = movm(vlo[j]);
  const bool far0 = 2 * t > g, far1 = 2 * t + 1 > g;
  const uint32_t mfar = (far0 ? 0x0000FFFFu : 0u) | (far1 ? 0xFFFF0000u : 0u);
  float slo[4][2], lg[2][2];
  uint32_t phi[4], plo[4], qml[4], qmh[4];
#pragma unroll
  for (int h = 0; h < 4; h++) {
    const int f = h == 0 ? 0 : h == 1 ? 3 : h == 2 ? 5 : 8, hf = h < 2 ? 2 : 7;
    const bool mine = (h & 1) ? t >= 2 : t < 2;
    qml[h] = mine ? qlo[hf] : 0u;
    qmh[h] = mine ? qhi[hf] : 0u;
    float a[4] = {0.f, 0.f, 0.f, 0.f}, c[4] = {0.f, 0.f, 0.f, 0.f};
    mma16816(a, qlo[f], qhi[f], qlo[f + 1], qhi[f + 1], klo[f], klo[f + 1]);
    mma16816(c, qlo[f], qhi[f], qlo[f + 1], qhi[f + 1], khi[f], khi[f + 1]);
    mma1688(a, qml[h], qmh[h], klo[hf]);
    mma1688(c, qml[h], qmh[h], khi[hf]);
    slo[h][0] = a[0];
    slo[h][1] = a[1];
    lg[h & 1][0] = far0 ? a[2] : c[2];
    lg[h & 1][1] = far1 ? a[3] : c[3];
    if (h & 1) softmax_two(lg, phi[h - 1], phi[h]);
  }
  TSIF(par == 0 && w == 1, 65);
  wg_sync(1 + par);
  TSIF(par == 0 && w == 1, 66);
  const bool nohist = (w == 0) && (b < 8);
  const uint4* hp = g_halo + ((b - 8) * 2 + par) * 224 + lane;
  uint32_t tg[7];
  if (w > 0) {
    const uint4 v0 = lds128(xa + (w - 1) * 2560), v1 = lds128(xa + (w - 1) * 2560 + 512), v2 = lds128(xa + (w - 1) * 2560 + 1024);
    const uint4 v3 = lds128(xa + (w - 1) * 2560 + 1536), v4 = lds128(xa + (w - 1) * 2560 + 2048);
    kpv[0] = v0.x; kpv[1] = v0.y; kpv[2] = v0.z; kpv[3] = v0.w; kpv[4] = v1.x; kpv[5] = v1.y; kpv[6] = v1.z; kpv[7] = v1.w;
    kpv[8] = v2.x; kpv[9] = v2.y; vpv[0] = v2.z; vpv[1] = v2.w; vpv[2] = v3.x; vpv[3] = v3.y; vpv[4] = v3.z; vpv[5] = v3.w;
    vpv[6] = v4.x; vpv[7] = v4.y; vpv[8] = v4.z; vpv[9] = v4.w;
  } else if (nohist) {
#pragma unroll
    for (int j = 0; j < 10; j++) kpv[j] = vpv[j] = 0u;
  } else {
    TSIF(par == 0, 77);
    halo_read(kpv, vpv, tg, hp);
  }
  if (w == 0 && !nohist) {
    int spins = 0;
    while (true) {
      bool ok = true;
#pragma unroll
      for (int j = 0; j < 7; j++) ok = ok && tg[j] == tag;
      if (__all_sync(0xffffffffu, ok) || ++spins > SPIN_LIMIT) break;
      halo_read(kpv, vpv, tg, hp);
    }
    TSIF(par == 0, 79);
  }
#pragma unroll
  for (int h = 0; h < 4; h++) {
    const int f = h == 0 ? 0 : h == 1 ? 3 : h == 2 ? 5 : 8, hf = h < 2 ? 2 : 7;
    float a[4] = {0.f, 0.f, 0.f, 0.f};
    mma16816(a, qlo[f], qhi[f], qlo[f + 1], qhi[f + 1], kpv[f], kpv[f + 1]);
    mma1688(a, qml[h], qmh[h], kpv[hf]);
    const float ninf = __int_as_float(0xff800000);
    lg[h & 1][0] = far0 ? (nohist ? ninf : a[0]) : slo[h][0];
    lg[h & 1][1] = far1 ? (nohist ? ninf : a[1]) : slo[h][1];
    if (h & 1) softmax_two(lg, plo[h - 1], plo[h]);
  }
  TSIF(par == 0 && w <= 1, 67 + w);
  uint32_t ov[20];
#pragma unroll
  for (int hp = 0; hp < 2; hp++) {
    const int hf = hp ? 7 : 2;
    float sh[4] = {0.f, 0.f, 0.f, 0.f}, i0 = 0.f, i1 = 0.f;
#pragma unroll
    for (int e = 0; e < 2; e++) {
      const int h = 2 * hp + e, f = h == 0 ? 0 : h == 1 ? 3 : h == 2 ? 5 : 8;
      const uint32_t a0 = plo[h] & mfar, a2 = plo[h] & ~mfar, a3 = phi[h] & mfar, c1 = phi[h] & ~mfar;
      float sum[4] = {0.f, 0.f, 0.f, 0.f};
      mma1688(sum, plo[h], phi[h], 0x3F803F80u);
      const float r0 = rcp(sum[0]), r1 = rcp(sum[2]);
#pragma unroll
      for (int j = f; j < f + 2; j++) {
        float o[4] = {0.f, 0.f, 0.f, 0.f};
        mma16816(o, a0, 0u, a2, a3, vpv[j], vlo[j]);
        mma1688(o, 0u, c1, vhi[j]);
        ov[2 * j] = pack2(o[0] * r0, o[1] * r0);
        ov[2 * j + 1] = pack2(o[2] * r1, o[3] * r1);
      }
      const bool mine = e ? g >= 4 : g < 4;
      mma16816(sh, a0, 0u, a2, a3, mine ? vpv[hf] : 0u, mine ? vlo[hf] : 0u);
      mma1688(sh, 0u, c1, mine ? vhi[hf] : 0u);
      if (e == 0 || t >= 2) {
        i0 = r0;
        i1 = r1;
      }
    }
    ov[2 * hf] = pack2(sh[0] * i0, sh[1] * i0);
    ov[2 * hf + 1] = pack2(sh[2] * i1, sh[3] * i1);
  }
  TS(32 + 4 * par + w);
  mbar_wait(sb + OFF_BAR + 8 * B_P1, 0);
  const uint32_t oa = sb + OFF_OA + (lane >> 4) * 2048 + (32 * w + 2 * (lane & 15) + par) * 16;
#pragma unroll
  for (int j = 0; j < 5; j++) stsm4(oa + 4096 * j, ov + 4 * j);
  TSIF(par == 0 && w == 0, 120);
  fence_async_smem();
  TSIF(par == 0 && w == 0, 121);
  __syncwarp();
  if (lane == 0) mbar_arrive(sb + OFF_BAR + 8 * B_ATTN);
  TSM(w == 0 || w == 2, 122 + par + (w == 2 ? 3 : 0));
}

struct Maps {
  CUtensorMap x, wm, wt, k, v, y, wo, qm, qt, om, ot;
};

__device__ __forceinline__ void load_stage(uint32_t sb, int kb, int b, const Maps& m) {
  const uint32_t st = sb + (kb & 3) * STAGE_BYTES, bar = sb + OFF_BAR + 8 * (B_FULL1 + (kb & 3));
  const int r = b >> 3, hg = b & 7, slab = kb - KV_KB;
  const bool kv = slab >= 0 && slab < 5;
  const uint32_t kbar = sb + OFF_BAR + 8 * (B_KV + slab), dst = sb + OFF_KVS + slab * KVS_BYTES;
  mbar_expect_tx(bar, STAGE_BYTES);
  if (kv) mbar_expect_tx(kbar, KVS_BYTES);
  tma_3d(st, &m.x, 64 * kb, 64 * r, 0, bar);
  tma_3d(st + ST_W, &m.wm, 80 * hg + (tail_first(hg) ? 16 : 0), 64 * kb, 0, bar);
  tma_3d(st + ST_WT, &m.wt, 80 * hg + (tail_first(hg) ? 0 : 64), 64 * kb, 0, bar);
  if (kv) tma_3d(dst, &m.k, 0, 32 * (b >> 1) - 3, 2 * slab + (b & 1), kbar);
  if (kv) tma_3d(dst + KVS_V, &m.v, 0, 32 * (b >> 1), 2 * slab + (b & 1), kbar);
}

__global__ void __launch_bounds__(NTHR, 1) fused_kernel(const __grid_constant__ Maps m, const Params p) {
  extern __shared__ __align__(1024) uint8_t smem[];
  const uint32_t sb = (uint32_t)__cvta_generic_to_shared(smem);
  const uint32_t bars = sb + OFF_BAR;
  const int tid = threadIdx.x, lane = tid & 31;
  int b = blockIdx.x;
  b = (((b & 63) >> 3) * 2 + (b & 1)) * 8 + (((b < 64 ? 0x6521 : 0x7430) >> (4 * ((b >> 1) & 3))) & 7);
  const int r = b >> 3, hg = b & 7;

  if (tid == T_ISSUE) {
    TSM(true, 0);
    mbar_init(bars + 8 * B_F0, 1);
    fence_async_smem();
    mbar_expect_tx(bars + 8 * B_F0, ST_WT);
    tma_3d(sb, &m.x, 0, 64 * r, 0, bars + 8 * B_F0);
    tma_3d(sb + ST_W, &m.wm, 80 * hg + (tail_first(hg) ? 16 : 0), 0, 0, bars + 8 * B_F0);
#pragma unroll
    for (int i = 0; i < 4; i++) mbar_init(bars + 8 * (B_FULL1 + i), 1);
    fence_async_smem();
    mbar_expect_tx(bars + 8 * B_FULL1, STAGE_BYTES - ST_WT);
    tma_3d(sb + ST_WT, &m.wt, 80 * hg + (tail_first(hg) ? 0 : 64), 0, 0, bars + 8 * B_FULL1);
    load_stage(sb, 1, b, m);
  } else if (tid == T_INIT) {
#pragma unroll
    for (int i = 0; i < B_F0; i++) mbar_init(bars + 8 * i, i < B_GATE ? 8 : i < B_CVD ? 4 : i == B_CVD ? 20 : 1);
    fence_async_smem();
  }
  const int warp = __shfl_sync(0xffffffffu, tid >> 5, 0), wg = warp >> 2, w = warp & 3;
  __syncthreads();

  if (wg == 3) {
    asm volatile("setmaxnreg.dec.sync.aligned.u32 56;");
    if (w == 0) {
      if (lane == 0) {
#pragma unroll 1
        for (int kb = 2; kb < 10; kb++) {
          if (kb >= 4) mbar_wait(bars + 8 * (kb == 7 ? B_E3 : B_EMPTY1 + (kb & 3)), (kb >> 3) & 1);
          TSIF(kb >= 4, 44 + kb);
          load_stage(sb, kb, b, m);
          TSIF(kb == 3, 60);
          if (kb == TRIG_KB) mbar_arrive(bars + 8 * B_LAST);
        }
        mbar_wait(bars + 8 * B_WOP, 0);
        mbar_wait(bars + 8 * WL_TRIG, 0);
        mbar_wait(bars + 8 * B_EPOCH, 0);
        flag_wait(g_cnt + C_W + 32 * hg, (lds32(sb + OFF_EPOCH) + 1) * 16);
        TS(30);
#pragma unroll 1
        for (int j = 0; j < 8; j++) {
          if (j >= 6) mbar_wait(bars + 8 * (B_EMPTY2 + j - 6), 0);
          if (j == 4) mbar_wait(bars + 8 * B_ATTN, 0);
          TSIF(j >= 6, 100 + j);
          mbar_expect_tx(bars + 8 * (B_FULL2 + j), j == 0 ? WO_BYTES : j == 5 ? O_BYTES + WO_BYTES + 512 : O_BYTES + WO_BYTES);
          bulk_load(sb + off_w(j), g_WO + (hg * 8 + step_src(hg, j)) * 800, WO_BYTES, bars + 8 * (B_FULL2 + j));
        }
        mbar_wait(bars + 8 * (B_EMPTY2 + 3), 0);
        mbar_expect_tx(bars + 8 * B_QF, O_BYTES);
        tma_2d(sb + OFF_QS, &m.qm, 80 * hg, 128 * r, bars + 8 * B_QF);
        tma_2d(sb + OFF_QT, &m.qt, 80 * hg + 64, 128 * r, bars + 8 * B_QF);
      }
    } else if (w == 1) {
      unsigned epoch = 0;
      if (lane == 0) {
        epoch = atomicAdd(g_cnt + C_LAUNCH, 1u) / NCTA;
        asm volatile("st.shared.u32 [%0], %1;" ::"r"(sb + OFF_EPOCH), "r"(epoch) : "memory");
        mbar_arrive(bars + 8 * B_EPOCH);
        mbar_wait(bars + 8 * B_KVD, 0);
        mbar_expect_tx(bars + 8 * B_HB, 5 * 4096);
#pragma unroll 1
        for (int c = 0; c < 5; c++) {
          if (c == 3) mbar_wait(bars + 8 * B_S3, 0);
          bulk_load(sb + off_ch(c) + U_BYTES, p.ssm_k + (5 * b + c) * SEQ, 4096, bars + 8 * B_HB);
        }
#pragma unroll
        for (int c = 0; c < 4; c++) mbar_expect_tx(bars + 8 * (B_U + c), c < 3 ? U_BYTES : 2 * U_BYTES);
        const uint4* usrc = g_U + 5 * b * U_PITCH;
        mbar_wait(bars + 8 * B_USIG, 0);
        flag_wait(g_cnt + C_PREP + 32 * (b & 15), (epoch + 1) * NCTA);
        TS(23);
#pragma unroll
        for (int c = 0; c < 5; c++) {
          if (c == 3) mbar_wait(bars + 8 * (B_U + 2), 0);
          bulk_load(sb + off_ch(c), usrc + c * U_PITCH, U_BYTES, bars + 8 * (B_U + (c < 3 ? c : 3)));
          TSIF(c == 0 || c == 4, 116 + (c >> 2));
        }
      }
      epoch = __shfl_sync(0xffffffffu, epoch, 0);
      if (lane < 8) {
        const int src = (b & ~7) | step_src(hg, lane);
        mbar_wait(bars + 8 * B_ATTN, 0);
        TS(20);
        bool seen = false;
#pragma unroll 1
        for (int spins = 0; spins < SPIN_LIMIT; spins++) {
          const bool now = !seen && (int)(flag_read(g_cnt + C_O + 32 * src) - (epoch + 1)) >= 0;
          if (now && lane >= 1 && lane < 4) bulk_load(sb + off_o(lane), g_O + src * 1280, O_BYTES, bars + 8 * (B_FULL2 + lane));
          seen = seen || now;
          if (__all_sync(0xff, seen)) break;
        }
        TS(21);
        if (lane == 5) bulk_load(sb + OFF_GATE, g_gate + 128 * r, 512, bars + 8 * (B_FULL2 + 5));
#pragma unroll 1
        for (int j = 4; j < 8; j++) {
          if (lane == j) {
            mbar_wait(bars + 8 * (j < 6 ? B_C34 : B_EMPTY2 + j - 6), 0);
            bulk_load(sb + off_o(j), g_O + src * 1280, O_BYTES, bars + 8 * (B_FULL2 + j));
          }
          __syncwarp(0xff);
        }
        TS(22);
      }
    } else if (w == 2) {
      mbar_wait(bars + 8 * B_PREP, 0);
      flag_signal(g_cnt + C_PREP, 16, lane);
      TS(25);
      if (lane == 0) {
        mbar_arrive(bars + 8 * B_USIG);
        mbar_expect_tx(bars + 8 * B_ORB, O_BYTES + 64);
        mbar_wait(bars + 8 * B_GATE, 0);
        publish(g_gate + 16 * b, sb + OFF_GATE + 64 * hg, 64, bars + 8 * B_ORB);
        mbar_wait(bars + 8 * B_ATTN, 0);
        publish(g_O + b * 1280, sb + OFF_OA, O_BYTES, bars + 8 * B_ORB);
        TS(74);
        mbar_wait(bars + 8 * B_ORB, 0);
        flag_bump(g_cnt + C_O + 32 * b);
        TS(26);
        mbar_arrive(bars + 8 * B_OSIG);
      }
    } else {
      if (lane == 0) {
        uint4* dst = g_WO + (hg * 8 + (r >> 1)) * 800 + (r & 1) * 80;
        mbar_wait(bars + 8 * B_S3, 0);
        asm volatile("cp.async.bulk.prefetch.L2.global [%0], 6400;" ::"l"(p.wo + b * 3200) : "memory");
        mbar_wait(bars + 8 * B_P1, 0);
        mbar_wait(bars + 8 * WB_TRIG, 0);
        mbar_expect_tx(bars + 8 * B_WST, WO_BYTES / 2);
        tma_3d(sb + OFF_WA, &m.wo, 0, 40 * r, 5 * hg, bars + 8 * B_WST);
        mbar_wait(bars + 8 * B_WST, 0);
#pragma unroll 1
        for (int n = 0; n < 5; n++) bulk_store(dst + 160 * n, sb + OFF_WA + 1280 * n, 1280);
        bulk_wait_read();
        mbar_expect_tx(bars + 8 * B_WST, WO_BYTES / 2);
#pragma unroll 1
        for (int n = 0; n < 5; n++) bulk_load(sb + OFF_WA + 1280 * n, dst + 160 * n, 1280, bars + 8 * B_WST);
        mbar_wait(bars + 8 * B_WST, 1);
        flag_bump(g_cnt + C_W + 32 * hg);
        mbar_arrive(bars + 8 * B_WOP);
        TS(71);
        mbar_expect_tx(bars + 8 * B_C34, 3 * U_BYTES);
        mbar_expect_tx(bars + 8 * B_YRB, 2 * U_BYTES);
#pragma unroll 1
        for (int c = 0; c < 5; c++) {
          mbar_wait(bars + 8 * (B_YST + c), 0);
          publish(g_U + (5 * b + c) * U_PITCH, sb + off_ch(c), U_BYTES, bars + 8 * (c < 3 ? B_C34 : B_YRB));
        }
        TS(75);
        mbar_wait(bars + 8 * B_C34, 0);
        mbar_wait(bars + 8 * B_YRB, 0);
        flag_bump(g_cnt + C_Y + 32 * (b >> 4));
        TS(27);
        mbar_arrive(bars + 8 * B_YSIG);
        mbar_expect_tx(bars + 8 * B_YFULL, 20480);
        flag_wait(g_cnt + C_Y + 32 * hg, (lds32(sb + OFF_EPOCH) + 1) * 16);
        TS(24);
        tma_2d(sb + OFF_YT, &m.y, 128 * r, 80 * hg, bars + 8 * B_YFULL);
        tma_2d(sb + OFF_YT + 10240, &m.y, 128 * r + 64, 80 * hg, bars + 8 * B_YFULL);
      }
    }
  } else {
    asm volatile("setmaxnreg.inc.sync.aligned.u32 152;");
    if (wg < 2) {
      float acc[120];
#pragma unroll
      for (int i = 0; i < 120; i++) acc[i] = 0.f;
      const uint32_t da = desc_lo(sb + wg * 8192, 16), db = desc_lo(sb + ST_W, 8192), dc = desc_lo(sb + ST_WT, 2048);
      mbar_wait(bars + 8 * B_F0, 0);
      TSIF(w == 0 && wg == 0, 1);
      wg_fence();
#pragma unroll
      for (int k = 0; k < 4; k++) WgSST<192>::mma<HI_SW128, HI_SW128>(acc, da + 2 * k, db + 128 * k, 1);
      wg_commit();
      mbar_wait(bars + 8 * B_FULL1, 0);
      wg_fence();
#pragma unroll
      for (int k = 0; k < 4; k++) WgSST<48>::mma<HI_SW128, HI_SW32>(acc + 96, da + 2 * k, dc + 32 * k, 1);
      wg_commit();
#pragma unroll 1
      for (int kb = 1; kb < 10; kb++) {
        mbar_wait(bars + 8 * (B_FULL1 + (kb & 3)), (kb >> 2) & 1);
        const uint32_t so = (kb & 3) * (STAGE_BYTES >> 4);
        wg_fence();
#pragma unroll
        for (int k = 0; k < 4; k++) {
          WgSST<192>::mma<HI_SW128, HI_SW128>(acc, da + so + 2 * k, db + so + 128 * k, 1);
          WgSST<48>::mma<HI_SW128, HI_SW32>(acc + 96, da + so + 2 * k, dc + so + 32 * k, 1);
        }
        wg_commit();
        wg_wait<1>();
        if (lane == 0) mbar_arrive(bars + 8 * (kb == 4 ? B_E3 : B_EMPTY1 + ((kb - 1) & 3)));
      }
      mbar_wait(bars + 8 * B_EPOCH, 0);
      const uint32_t tag = lds32(sb + OFF_EPOCH) + 1;
      mbar_wait(bars + 8 * B_S3, 0);
      wg_wait<0>();
      pin<120>(acc);
      if (lane == 0) mbar_arrive(bars + 8 * B_P1);
      TSM(w == 0, 3 + wg);
      attention(acc, sb, b, wg, w, lane, tag);
    } else {
      const int tw = tid & 127, chl = 64 * (b & 1) + 8 * w + (lane >> 2);
      uint4* up = g_U + chl * U_PITCH + ((4 * (b >> 1) + (lane & 3)) ^ ((b >> 2) & 1));
      uint2 sw[10];
      uint32_t dv = 0;
      if (lane < 5) dv = __ldg(reinterpret_cast<const unsigned short*>(p.ssm_D) + 5 * b + lane);
#pragma unroll
      for (int i = 0; i < 10; i++) sw[i] = ldg64(reinterpret_cast<const uint2*>(p.shift_k) + chl + 128 * (i >> 1) + 32 * (i & 1));
      uint32_t tab[12];
      uint32_t tt[2];
      fft_tables(tab, tw);
      fft_twiddles(tt, tw);
      uint4 res[10];
#pragma unroll
      for (int i = 0; i < 10; i++) res[i] = make_uint4(0, 0, 0, 0);
#pragma unroll 1
      for (int slab = 0; slab < 5; slab++) {
#pragma unroll
        for (int i = 0; i < 8; i++) res[i] = res[i + 2];
        prep_slab(res + 8, sw, sb, slab, w, lane);
        TSIF(w == 0, 99 + 4 * slab);
#pragma unroll
        for (int i = 0; i < 8; i++) sw[i] = sw[i + 2];
      }
      TSIF(w == 0, 28);
      __syncwarp();
      if (lane == 0) mbar_arrive(bars + 8 * B_KVD + ((res[8].x ^ res[9].x) & p.zero));
      mbar_wait(bars + 8 * B_KVD, 0);
      fft_tables_store(tab, sb, tw);
      mbar_wait(bars + 8 * B_LAST, 0);
#pragma unroll
      for (int i = 0; i < 10; i++) up[(128 * (i >> 1) + 32 * (i & 1)) * U_PITCH] = res[i];
      __syncwarp();
      if (lane == 0) mbar_arrive(bars + 8 * B_PREP);
      TSIF(w == 0, 5);
      mbar_wait(bars + 8 * B_LAST, 0);
      prep_gate(p, sb, b, w, lane);
      __syncwarp();
      if (lane == 0) mbar_arrive(bars + 8 * B_GATE);
      TSIF(w == 0, 72);
      mbar_wait(bars + 8 * B_HB, 0);
      TSIF(w == 0, 2);
      const uint32_t ha = sb + U_BYTES + ((tw >> 3) * 16 + 8 + (tw & 7)) * 16;
      uint4 hv[5];
#pragma unroll
      for (int c = 0; c < 5; c++) hv[c] = lds128(ha + off_ch(c));
      __syncwarp();
#pragma unroll
      for (int c = 0; c < 5; c++) sts128((ha ^ 16) + off_ch(c), hv[c].x, hv[c].y, hv[c].z, hv[c].w);
      asm volatile("st.shared.v2.u32 [%0], {%1, %2};" ::"r"(sb + OFF_TT + 8 * tw), "r"(tt[0]), "r"(tt[1]) : "memory");
      if (tw < 5) asm volatile("st.shared.f32 [%0], %1;" ::"r"(sb + OFF_D + 4 * tw), "f"(bf_lo(dv) * 0.125f) : "memory");
      fence_async_smem();
      __syncwarp();
      if (lane == 0) mbar_arrive(bars + 8 * B_HA);
      TSIF(w == 0, 6);
    }

    FftConst fc;
    TSM(w == 0 && wg == 0, 104);
    mbar_wait(bars + 8 * B_HA, 0);
    fft_matrices(fc, sb, w, lane);
    TSM(w == 0 && wg == 0, 105);
    TSM(w == 0 && wg == 2, 124);
#pragma unroll 1
    for (uint32_t tasks = wg == 0 ? TASK0 : wg == 1 ? TASK1 : TASK2; tasks; tasks >>= 4) {
      const int c = (tasks & 7) - 1;
      conv_channel(fc, sb, c, wg, w, lane);
      if (lane == 0) mbar_arrive(bars + 8 * (B_YST + c));
      TSM(w == 0, 10 + c);
    }

    if (wg < 2) {
      const int g = lane >> 2;
      float acc[40];
#pragma unroll
      for (int i = 0; i < 40; i++) acc[i] = 0.f;
      const uint32_t da = desc_lo(sb + wg * 1024, 2048), db = desc_lo(sb, 2560);
      mbar_wait(bars + 8 * B_ORB, 0);
      mbar_wait(bars + 8 * B_FULL2, 0);
      mbar_wait(bars + 8 * B_CVD, 0);
      TSM(w == 0, 15 + wg);
#pragma unroll 1
      for (int j = 0; j < 8; j++) {
        mbar_wait(bars + 8 * (B_FULL2 + j), 0);
        TSM(w == 0 && wg == 0, 44 + (j < 4 ? j : j + 6));
        const uint32_t oa = da + (off_o(j) >> 4), ob = db + (off_w(j) >> 4);
        wg_fence();
#pragma unroll
        for (int k = 0; k < 5; k++) WgSST<80>::mma<HI_NONE, HI_SW32>(acc, oa + 256 * k, ob + 32 * k, 1);
        wg_commit();
        wg_wait<1>();
        if (j >= 1 && j <= 4 && lane == 0) mbar_arrive(bars + 8 * (B_EMPTY2 + j - 1));
      }
      TSIF(w == 0 && wg == 0, 113);
      const int tr = 64 * wg + 16 * w + (lane & 15);
      const uint32_t fm = sb + OFF_QS + tr * 128, fx = (lane >> 4) ^ (tr & 7);
      const uint32_t ft = sb + OFF_QT + tr * 32 + (((lane >> 4) ^ (tr >> 2)) & 1) * 16;
      const float g0 = __uint_as_float(lds32(sb + OFF_GATE + (64 * wg + 16 * w + g) * 4));
      const float g1 = __uint_as_float(lds32(sb + OFF_GATE + (64 * wg + 16 * w + 8 + g) * 4));
      const uint32_t ga = pack2(g0, g0), gb = pack2(g1, g1);
      const uint32_t na = pack2(1.f - g0, 1.f - g0), nb = pack2(1.f - g1, 1.f - g1);

      uint32_t qf[20];
      mbar_wait(bars + 8 * B_QF, 0);
      TSM(w == 0 && wg == 0, 99);
#pragma unroll
      for (int j = 0; j < 5; j++) ldsm4(qf + 4 * j, j < 4 ? fm + ((fx ^ (2 * j)) << 4) : ft);
#pragma unroll
      for (int i = 0; i < 20; i++) {
        qf[i] = bmul((i & 1) ? gb : ga, qf[i]);
        asm volatile("" : "+r"(qf[i]));
      }

      wg_wait<0>();
      pin<40>(acc);
      TSM(w == 0, 17 + wg);
      uint32_t pb[20];
#pragma unroll
      for (int j = 0; j < 10; j++) {
        pb[2 * j] = bmul(na, pack2(acc[4 * j], acc[4 * j + 1]));
        pb[2 * j + 1] = bmul(nb, pack2(acc[4 * j + 2], acc[4 * j + 3]));
        asm volatile("" : "+r"(pb[2 * j]), "+r"(pb[2 * j + 1]));
      }
      const uint32_t ya = sb + OFF_YT + wg * 10240 + ((lane >> 4) * 8 + (lane & 7)) * 128 +
                          (((2 * w + (((lane >> 3) & 1) ^ wg)) ^ (lane & 7)) << 4);
      mbar_wait(bars + 8 * B_YFULL, 0);
      TSM(w == 0 && wg == 0, 19);
#pragma unroll
      for (int j = 0; j < 5; j++) {
        uint32_t y[4];
        ldsm4t(y, ya + 2048 * j);
#pragma unroll
        for (int i = 0; i < 4; i++)
          qf[4 * j + i] = bfma(qf[4 * j + i], y[i], pb[4 * j + i]);
      }
#pragma unroll
      for (int j = 0; j < 5; j++) stsm4(j < 4 ? fm + ((fx ^ (2 * j)) << 4) : ft, qf + 4 * j);
      fence_async_smem();
      __syncwarp();
      if (lane == 0) {
        const int row = 64 * wg + 16 * w;
        asm volatile("cp.async.bulk.tensor.2d.global.shared::cta.bulk_group [%0, {%2, %3}], [%1];"
                     ::"l"(&m.om), "r"(sb + OFF_QS + row * 128), "r"(80 * hg), "r"(128 * r + row) : "memory");
        asm volatile("cp.async.bulk.tensor.2d.global.shared::cta.bulk_group [%0, {%2, %3}], [%1];"
                     ::"l"(&m.ot), "r"(sb + OFF_QT + row * 32), "r"(80 * hg + 64), "r"(128 * r + row) : "memory");
        asm volatile("cp.async.bulk.commit_group;\ncp.async.bulk.wait_group.read 0;" ::: "memory");
      }
      TSM(w == 0 || w == 3, 40 + 2 * wg + (w & 1));
    }
  }
}

typedef CUresult (*EncodeFn)(CUtensorMap*, CUtensorMapDataType, cuuint32_t, void*, const cuuint64_t*, const cuuint64_t*,
                             const cuuint32_t*, const cuuint32_t*, CUtensorMapInterleave, CUtensorMapSwizzle,
                             CUtensorMapL2promotion, CUtensorMapFloatOOBfill);

void encode(EncodeFn fn, CUtensorMap* tm, const void* base, int rank, const cuuint64_t* dims, const cuuint64_t* strides,
            const cuuint32_t* box, CUtensorMapSwizzle swz) {
  const cuuint32_t ones[3] = {1, 1, 1};
  fn(tm, CU_TENSOR_MAP_DATA_TYPE_BFLOAT16, rank, const_cast<void*>(base), dims, strides, box, ones,
     CU_TENSOR_MAP_INTERLEAVE_NONE, swz, CU_TENSOR_MAP_L2_PROMOTION_L2_128B, CU_TENSOR_MAP_FLOAT_OOB_FILL_NONE);
}

}

extern "C" void kernel_launch(void* const* d_in, const int* in_sizes, int n_in, void* d_out, int out_size) {
  (void)in_sizes; (void)n_in; (void)out_size;
  Params p;
  p.q = (const __nv_bfloat16*)d_in[0];
  p.k = (const __nv_bfloat16*)d_in[1];
  p.v = (const __nv_bfloat16*)d_in[2];
  p.shift_k = (const __nv_bfloat16*)d_in[3];
  p.ssm_k = (const __nv_bfloat16*)d_in[4];
  p.ssm_D = (const __nv_bfloat16*)d_in[5];
  p.wqkv = (const __nv_bfloat16*)d_in[7];
  p.wo = (const __nv_bfloat16*)d_in[8];
  p.gate_w = (const __nv_bfloat16*)d_in[9];
  p.out = (__nv_bfloat16*)d_out;
  p.zero = 0;

  static EncodeFn fn = nullptr;
  static void* yaddr = nullptr;
  if (!fn) {
    cudaDriverEntryPointQueryResult qr;
    void* f = nullptr;
    cudaGetDriverEntryPoint("cuTensorMapEncodeTiled", &f, cudaEnableDefault, &qr);
    fn = (EncodeFn)f;
    cudaGetSymbolAddress(&yaddr, g_U);
    cudaFuncSetAttribute(fused_kernel, cudaFuncAttributeMaxDynamicSharedMemorySize, SMEM_BYTES);
  }
  Maps m;
  {
    const cuuint64_t dims[3] = {640, 1024, 2}, st[2] = {2560, 1280};
    const cuuint32_t box[3] = {64, 64, 2};
    encode(fn, &m.x, p.q, 3, dims, st, box, CU_TENSOR_MAP_SWIZZLE_128B);
  }
  {
    const cuuint64_t dims[3] = {640, 640, 3}, st[2] = {3840, 1280};
    const cuuint32_t box[3] = {64, 64, 3}, boxt[3] = {16, 64, 3};
    encode(fn, &m.wm, p.wqkv, 3, dims, st, box, CU_TENSOR_MAP_SWIZZLE_128B);
    encode(fn, &m.wt, p.wqkv, 3, dims, st, boxt, CU_TENSOR_MAP_SWIZZLE_32B);
  }
  {
    const cuuint64_t dims[3] = {64, 2048, 10}, st[2] = {1280, 128};
    const cuuint32_t boxk[3] = {64, 35, 1}, boxv[3] = {64, 32, 1};
    encode(fn, &m.k, p.k, 3, dims, st, boxk, CU_TENSOR_MAP_SWIZZLE_128B);
    encode(fn, &m.v, p.v, 3, dims, st, boxv, CU_TENSOR_MAP_SWIZZLE_128B);
  }
  {
    const cuuint64_t dims[3] = {16, 640, 40}, st[2] = {1280, 32};
    const cuuint32_t box[3] = {16, 40, 5};
    encode(fn, &m.wo, p.wo, 3, dims, st, box, CU_TENSOR_MAP_SWIZZLE_32B);
  }
  {
    const cuuint64_t dims[2] = {2048, 640}, st[1] = {U_PITCH * 16};
    const cuuint32_t box[2] = {64, 80};
    encode(fn, &m.y, yaddr, 2, dims, st, box, CU_TENSOR_MAP_SWIZZLE_128B);
  }
  {
    const cuuint64_t dims[2] = {640, 2048}, st[1] = {1280};
    const cuuint32_t bqm[2] = {64, 128}, bqt[2] = {16, 128}, bom[2] = {64, 16}, bot[2] = {16, 16};
    encode(fn, &m.qm, p.q, 2, dims, st, bqm, CU_TENSOR_MAP_SWIZZLE_128B);
    encode(fn, &m.qt, p.q, 2, dims, st, bqt, CU_TENSOR_MAP_SWIZZLE_32B);
    encode(fn, &m.om, p.out, 2, dims, st, bom, CU_TENSOR_MAP_SWIZZLE_128B);
    encode(fn, &m.ot, p.out, 2, dims, st, bot, CU_TENSOR_MAP_SWIZZLE_32B);
  }
  fused_kernel<<<NCTA, NTHR, SMEM_BYTES>>>(m, p);
}
```

```cpp
#include <cuda.h>
#include <cuda_bf16.h>
#include <cuda_runtime.h>
#include <stdint.h>

namespace {

constexpr int SEQ = 2048, DIM = 640, NCTA = 128, NTHR = 512;

#define TRIG_KB 9
#define KV_KB 2
#define DEV_EXIT 0
#define FENCE_LO 0
#define FENCE_HI 0
#define WB_TRIG B_USIG
#define T_ISSUE 256
#define T_ISS2 288
#define T_INIT 448
#define TASK0 0x3
#define TASK1 0x52
#define TASK2 0x41
#define WL_TRIG B_WOP

constexpr uint32_t STAGE_BYTES = 47104, ST_W = 16384, ST_WT = 40960;
constexpr uint32_t O_BYTES = 20480, WO_BYTES = 12800;
constexpr uint32_t OFF_OA = 0;
constexpr uint32_t OFF_QS = 3 * O_BYTES, OFF_QT = OFF_QS + 16384;
constexpr uint32_t OFF_WC = 81920;
constexpr uint32_t OFF_WA = 94720;
constexpr uint32_t OFF_GATE = 145920;
constexpr uint32_t OFF_TT = 146432;
constexpr uint32_t OFF_KVX = 148480;
constexpr uint32_t OFF_CH3 = 163840;
constexpr uint32_t CH_BYTES = 12288, U_BYTES = 4096;
constexpr uint32_t OFF_FT = 225280, OFF_GT = 229376;
constexpr uint32_t OFF_CH0 = 188416;
constexpr uint32_t OFF_KVS = OFF_CH0, KVS_V = 4480, KVS_BYTES = 8576;
constexpr uint32_t OFF_YT = 163840;
constexpr uint32_t OFF_BAR = 231936;
constexpr uint32_t SMEM_BYTES = OFF_BAR + 512;

enum : uint32_t {
  B_EMPTY1 = 0, B_S3 = 3, B_E3 = 4, B_EMPTY2 = 5, B_ATTN = 9, B_P1 = 10,
  B_GATE = 11, B_HA = 12, B_KVD = 13, B_PREP = 14, B_YST = 15,
  B_CVD = 20,
  B_FULL2 = 21, B_U = 29, B_KV = 33, B_HB = 38, B_C34 = 39, B_YRB = 40, B_YFULL = 41, B_EPOCH = 42, B_LAST = 43, B_OSIG = 44,
  B_WOP = 45, B_USIG = 46, B_WST = 47, B_QF = 48, B_ORB = 49, B_YSIG = 50,
  B_F0 = 51, B_FULL1 = 52, B_F1 = 56
};
constexpr uint32_t OFF_EPOCH = OFF_BAR + 8 * 58, OFF_D = OFF_BAR + 8 * 60;
__device__ __forceinline__ uint32_t off_o(int j) { return j < 4 ? OFF_OA + j * O_BYTES : j < 6 ? OFF_CH0 + (j - 4) * O_BYTES : OFF_OA + (j - 6) * O_BYTES; }
__device__ __forceinline__ uint32_t off_w(int j) { return j < 4 ? OFF_WA + j * WO_BYTES : j == 4 ? OFF_KVX : j == 5 ? OFF_WC : OFF_WA + (j - 6) * WO_BYTES; }
__device__ __forceinline__ int step_src(int hg, int j) { return j == 0 ? hg : j <= hg ? j - 1 : j; }
__device__ __forceinline__ bool tail_first(int hg) { return (hg & 3) == 3; }
__device__ __forceinline__ uint32_t off_ch(int c) { return (c < 3 ? OFF_CH0 : OFF_CH3 - 3 * CH_BYTES) + c * CH_BYTES; }

#define U_PITCH 264
__device__ __align__(1024) uint4 g_U[DIM * U_PITCH];
__device__ uint4 g_O[NCTA * 1280];
__device__ uint4 g_WO[64 * 800];
__device__ uint4 g_halo[NCTA * 2 * 7 * 32];
__device__ __align__(128) float g_gate[SEQ];
__device__ unsigned g_cnt[32 * (1 + 2 * 16 + 8 + NCTA)];
constexpr int C_LAUNCH = 0, C_PREP = 32, C_Y = 32 * 17, C_W = 32 * 33, C_O = 32 * 41;

#define TSM(cond, slot) do { } while (0)
#define TSIF(cond, slot) do { if (__LINE__ >= FENCE_LO && __LINE__ < FENCE_HI) sched_fence(); } while (0)
__device__ __forceinline__ void sched_fence() {
  asm volatile("{\n.reg .pred p;\n.reg .u32 c;\nmov.u32 c, %%clock;\nsetp.eq.u32 p, c, 0;\n@p st.shared.u32 [%0], c;\n}"
               ::"r"(1024 + OFF_EPOCH + 4) : "memory");
}
#define TS(slot) TSIF(true, slot)

struct Params {
  const __nv_bfloat16 *q, *k, *v, *shift_k, *ssm_k, *ssm_D, *wqkv, *wo, *gate_w;
  __nv_bfloat16* out;
  uint32_t zero;
};

constexpr int SPIN_LIMIT = 1 << 17;

__device__ __forceinline__ void mbar_init(uint32_t bar, uint32_t count) {
  asm volatile("mbarrier.init.shared::cta.b64 [%0], %1;" ::"r"(bar), "r"(count) : "memory");
}
__device__ __forceinline__ void mbar_expect_tx(uint32_t bar, uint32_t bytes) {
  asm volatile("mbarrier.arrive.expect_tx.shared::cta.b64 _, [%0], %1;" ::"r"(bar), "r"(bytes) : "memory");
}
__device__ __forceinline__ void mbar_arrive(uint32_t bar) {
  asm volatile("mbarrier.arrive.shared::cta.b64 _, [%0];" ::"r"(bar) : "memory");
}
__device__ __forceinline__ void mbar_wait(uint32_t bar, uint32_t parity) {
  uint32_t ok;
  int spins = 0;
  do {
      asm volatile("{\n.reg .pred p;\nmbarrier.try_wait.parity.shared::cta.b64 p, [%1], %2;\nselp.b32 %0, 1, 0, p;\n}"
                   : "=r"(ok) : "r"(bar), "r"(parity) : "memory");
    if (++spins > SPIN_LIMIT) break;
  } while (!ok);
}
__device__ __forceinline__ unsigned flag_read(const unsigned* p) {
  unsigned v;
  asm volatile("ld.relaxed.gpu.global.u32 %0, [%1];" : "=r"(v) : "l"(p) : "memory");
  return v;
}
__device__ __forceinline__ void flag_poll(const unsigned* p, unsigned target) {
  unsigned v;
  int spins = 0;
  do {
    asm volatile("ld.relaxed.gpu.global.u32 %0, [%1];" : "=r"(v) : "l"(p) : "memory");
    if (++spins > SPIN_LIMIT) break;
  } while ((int)(v - target) < 0);
}
__device__ __forceinline__ void flag_wait(const unsigned* p, unsigned target) {
  flag_poll(p, target);
}
__device__ __forceinline__ void flag_signal(unsigned* p, int n, int lane) {
  if (lane == 0) asm volatile("fence.release.gpu;" ::: "memory");
  __syncwarp();
  if (lane < n) asm volatile("red.relaxed.gpu.global.add.u32 [%0], 1;" ::"l"(p + 32 * lane) : "memory");
}
__device__ __forceinline__ void flag_bump(unsigned* p) {
  asm volatile("red.relaxed.gpu.global.add.u32 [%0], 1;" ::"l"(p) : "memory");
}
__device__ __forceinline__ void fence_async_smem() { asm volatile("fence.proxy.async.shared::cta;" ::: "memory"); }
__device__ __forceinline__ void wg_sync(int id) { asm volatile("bar.sync %0, 128;" ::"r"(id) : "memory"); }

__device__ __forceinline__ void tma_2d(uint32_t dst, const CUtensorMap* tm, int c0, int c1, uint32_t bar) {
  asm volatile("cp.async.bulk.tensor.2d.shared::cluster.global.mbarrier::complete_tx::bytes [%0], [%1, {%3, %4}], [%2];"
               ::"r"(dst), "l"(tm), "r"(bar), "r"(c0), "r"(c1) : "memory");
}
__device__ __forceinline__ void tma_3d(uint32_t dst, const CUtensorMap* tm, int c0, int c1, int c2, uint32_t bar) {
  asm volatile("cp.async.bulk.tensor.3d.shared::cluster.global.mbarrier::complete_tx::bytes [%0], [%1, {%3, %4, %5}], [%2];"
               ::"r"(dst), "l"(tm), "r"(bar), "r"(c0), "r"(c1), "r"(c2) : "memory");
}
__device__ __forceinline__ void bulk_load(uint32_t dst, const void* src, uint32_t bytes, uint32_t bar) {
  asm volatile("cp.async.bulk.shared::cluster.global.mbarrier::complete_tx::bytes [%0], [%1], %2, [%3];"
               ::"r"(dst), "l"(src), "r"(bytes), "r"(bar) : "memory");
}
__device__ __forceinline__ void bulk_store(void* dst, uint32_t src, uint32_t bytes) {
  asm volatile("cp.async.bulk.global.shared::cta.bulk_group [%0], [%1], %2;" ::"l"(dst), "r"(src), "r"(bytes) : "memory");
}
__device__ __forceinline__ void bulk_wait_read() {
  asm volatile("cp.async.bulk.commit_group;\ncp.async.bulk.wait_group.read 0;" ::: "memory");
}

__device__ __forceinline__ void publish(void* dst, uint32_t src, uint32_t bytes, uint32_t bar) {
  bulk_store(dst, src, bytes);
  bulk_wait_read();
  bulk_load(src, dst, bytes, bar);
}

__device__ __forceinline__ void wg_fence() { asm volatile("wgmma.fence.sync.aligned;" ::: "memory"); }
__device__ __forceinline__ void wg_commit() { asm volatile("wgmma.commit_group.sync.aligned;" ::: "memory"); }
template <int N> __device__ __forceinline__ void wg_wait() { asm volatile("wgmma.wait_group.sync.aligned %0;" ::"n"(N) : "memory"); }
__device__ __forceinline__ uint32_t desc_lo(uint32_t addr, uint32_t lbo) { return ((addr & 0x3FFFF) >> 4) | ((lbo >> 4) << 16); }
constexpr uint32_t desc_hi(uint32_t sbo, uint32_t swz) { return (sbo >> 4) | (swz << 30); }
constexpr uint32_t HI_SW128 = desc_hi(1024, 1), HI_SW64 = desc_hi(512, 2), HI_SW32 = desc_hi(256, 3), HI_NONE = desc_hi(128, 0);
template <int N> __device__ __forceinline__ void pin(float* d) {
#pragma unroll
  for (int i = 0; i < N; i++) asm volatile("" : "+f"(d[i])::"memory");
}

__device__ __forceinline__ uint32_t lds32(uint32_t a) {
  uint32_t v;
  asm volatile("ld.volatile.shared.u32 %0, [%1];" : "=r"(v) : "r"(a) : "memory");
  return v;
}
__device__ __forceinline__ uint2 ldg64(const void* a) {
  uint2 v;
  asm volatile("ld.global.nc.v2.u32 {%0, %1}, [%2];" : "=r"(v.x), "=r"(v.y) : "l"(a) : "memory");
  return v;
}
__device__ __forceinline__ void ldsm4(uint32_t* r, uint32_t a) {
  asm volatile("ldmatrix.sync.aligned.m8n8.x4.shared.b16 {%0, %1, %2, %3}, [%4];"
               : "=r"(r[0]), "=r"(r[1]), "=r"(r[2]), "=r"(r[3]) : "r"(a) : "memory");
}
__device__ __forceinline__ void ldsm4t(uint32_t* r, uint32_t a) {
  asm volatile("ldmatrix.sync.aligned.m8n8.x4.trans.shared.b16 {%0, %1, %2, %3}, [%4];"
               : "=r"(r[0]), "=r"(r[1]), "=r"(r[2]), "=r"(r[3]) : "r"(a) : "memory");
}
__device__ __forceinline__ uint2 lds64(uint32_t a) {
  uint2 v;
  asm volatile("ld.shared.v2.u32 {%0, %1}, [%2];" : "=r"(v.x), "=r"(v.y) : "r"(a) : "memory");
  return v;
}
__device__ __forceinline__ uint4 lds128(uint32_t a) {
  uint4 v;
  asm volatile("ld.shared.v4.u32 {%0, %1, %2, %3}, [%4];" : "=r"(v.x), "=r"(v.y), "=r"(v.z), "=r"(v.w) : "r"(a) : "memory");
  return v;
}
__device__ __forceinline__ void sts128(uint32_t a, uint32_t x, uint32_t y, uint32_t z, uint32_t w) {
  asm volatile("st.shared.v4.u32 [%0], {%1, %2, %3, %4};" ::"r"(a), "r"(x), "r"(y), "r"(z), "r"(w) : "memory");
}
__device__ __forceinline__ void stsm4(uint32_t a, const uint32_t* r) {
  asm volatile("stmatrix.sync.aligned.m8n8.x4.shared.b16 [%0], {%1, %2, %3, %4};" ::"r"(a), "r"(r[0]), "r"(r[1]), "r"(r[2]), "r"(r[3]) : "memory");
}
__device__ __forceinline__ uint32_t pack2(float lo, float hi) {
  uint32_t r;
  asm("cvt.rn.bf16x2.f32 %0, %1, %2;" : "=r"(r) : "f"(hi), "f"(lo));
  return r;
}
__device__ __forceinline__ uint32_t movm(uint32_t a) {
  uint32_t d;
  asm volatile("movmatrix.sync.aligned.m8n8.trans.b16 %0, %1;" : "=r"(d) : "r"(a));
  return d;
}
__device__ __forceinline__ uint32_t bmul(uint32_t a, uint32_t b) {
  uint32_t d;
  asm("mul.rn.bf16x2 %0, %1, %2;" : "=r"(d) : "r"(a), "r"(b));
  return d;
}
__device__ __forceinline__ uint32_t badd(uint32_t a, uint32_t b) {
  uint32_t d;
  asm("add.rn.bf16x2 %0, %1, %2;" : "=r"(d) : "r"(a), "r"(b));
  return d;
}
__device__ __forceinline__ uint32_t bfma(uint32_t a, uint32_t b, uint32_t c) {
  uint32_t d;
  asm("fma.rn.bf16x2 %0, %1, %2, %3;" : "=r"(d) : "r"(a), "r"(b), "r"(c));
  return d;
}
__device__ __forceinline__ float bf_lo(uint32_t x) { return __uint_as_float(x << 16); }
__device__ __forceinline__ float bf_hi(uint32_t x) { return __uint_as_float(x & 0xFFFF0000u); }
__device__ __forceinline__ float ex2(float x) {
  float y;
  asm("ex2.approx.ftz.f32 %0, %1;" : "=f"(y) : "f"(x));
  return y;
}
__device__ __forceinline__ float rcp(float x) {
  float y;
  asm("rcp.approx.ftz.f32 %0, %1;" : "=f"(y) : "f"(x));
  return y;
}
__device__ __forceinline__ void mma16816(float* d, uint32_t a0, uint32_t a1, uint32_t a2, uint32_t a3, uint32_t b0, uint32_t b1) {
  asm volatile("mma.sync.aligned.m16n8k16.row.col.f32.bf16.bf16.f32 {%0, %1, %2, %3}, {%4, %5, %6, %7}, {%8, %9}, {%0, %1, %2, %3};"
               : "+f"(d[0]), "+f"(d[1]), "+f"(d[2]), "+f"(d[3])
               : "r"(a0), "r"(a1), "r"(a2), "r"(a3), "r"(b0), "r"(b1));
}
__device__ __forceinline__ void mma1688(float* d, uint32_t a0, uint32_t a1, uint32_t b0) {
  asm volatile("mma.sync.aligned.m16n8k8.row.col.f32.bf16.bf16.f32 {%0, %1, %2, %3}, {%4, %5}, {%6}, {%0, %1, %2, %3};"
               : "+f"(d[0]), "+f"(d[1]), "+f"(d[2]), "+f"(d[3])
               : "r"(a0), "r"(a1), "r"(b0));
}

template <int N> struct WgRS;
template <int N> struct WgSST;
template <> struct WgRS<32> {
  template <uint32_t HB>
  static __device__ __forceinline__ void mma(float* d, const uint32_t* a, uint32_t db) {
    asm volatile("{\n.reg .pred p;\n.reg .b64 db;\nsetp.ne.b32 p, %22, 0;\n"
      "mov.b64 db, {%20, %21};\n"
      "wgmma.mma_async.sync.aligned.m64n32k16.f32.bf16.bf16 {"
      "%0, %1, %2, %3, %4, %5, %6, %7, %8, %9, %10, %11, %12, %13, %14, %15"
      "}, {%16, %17, %18, %19}, db, p, 1, 1, 1;\n}\n"
      : "+f"(d[0]), "+f"(d[1]), "+f"(d[2]), "+f"(d[3]), "+f"(d[4]), "+f"(d[5]), "+f"(d[6]), "+f"(d[7]),
        "+f"(d[8]), "+f"(d[9]), "+f"(d[10]), "+f"(d[11]), "+f"(d[12]), "+f"(d[13]), "+f"(d[14]), "+f"(d[15])
      : "r"(a[0]), "r"(a[1]), "r"(a[2]), "r"(a[3]), "r"(db), "n"(HB), "n"(1));
  }
  template <uint32_t HB>
  static __device__ __forceinline__ void set(float* d, const uint32_t* a, uint32_t db) {
    asm volatile("{\n.reg .pred p;\n.reg .b64 db;\nsetp.ne.b32 p, %22, 0;\n"
      "mov.b64 db, {%20, %21};\n"
      "wgmma.mma_async.sync.aligned.m64n32k16.f32.bf16.bf16 {"
      "%0, %1, %2, %3, %4, %5, %6, %7, %8, %9, %10, %11, %12, %13, %14, %15"
      "}, {%16, %17, %18, %19}, db, p, 1, 1, 1;\n}\n"
      : "=f"(d[0]), "=f"(d[1]), "=f"(d[2]), "=f"(d[3]), "=f"(d[4]), "=f"(d[5]), "=f"(d[6]), "=f"(d[7]),
        "=f"(d[8]), "=f"(d[9]), "=f"(d[10]), "=f"(d[11]), "=f"(d[12]), "=f"(d[13]), "=f"(d[14]), "=f"(d[15])
      : "r"(a[0]), "r"(a[1]), "r"(a[2]), "r"(a[3]), "r"(db), "n"(HB), "n"(0));
  }
};
template <> struct WgRS<64> {
  template <uint32_t HB>
  static __device__ __forceinline__ void mma(float* d, const uint32_t* a, uint32_t db) {
    asm volatile("{\n.reg .pred p;\n.reg .b64 db;\nsetp.ne.b32 p, %38, 0;\n"
      "mov.b64 db, {%36, %37};\n"
      "wgmma.mma_async.sync.aligned.m64n64k16.f32.bf16.bf16 {"
      "%0, %1, %2, %3, %4, %5, %6, %7, %8, %9, %10, %11, %12, %13, %14, %15, "
      "%16, %17, %18, %19, %20, %21, %22, %23, %24, %25, %26, %27, %28, %29, %30, %31"
      "}, {%32, %33, %34, %35}, db, p, 1, 1, 1;\n}\n"
      : "+f"(d[0]), "+f"(d[1]), "+f"(d[2]), "+f"(d[3]), "+f"(d[4]), "+f"(d[5]), "+f"(d[6]), "+f"(d[7]),
        "+f"(d[8]), "+f"(d[9]), "+f"(d[10]), "+f"(d[11]), "+f"(d[12]), "+f"(d[13]), "+f"(d[14]), "+f"(d[15]),
        "+f"(d[16]), "+f"(d[17]), "+f"(d[18]), "+f"(d[19]), "+f"(d[20]), "+f"(d[21]), "+f"(d[22]), "+f"(d[23]),
        "+f"(d[24]), "+f"(d[25]), "+f"(d[26]), "+f"(d[27]), "+f"(d[28]), "+f"(d[29]), "+f"(d[30]), "+f"(d[31])
      : "r"(a[0]), "r"(a[1]), "r"(a[2]), "r"(a[3]), "r"(db), "n"(HB), "n"(1));
  }
  template <uint32_t HB>
  static __device__ __forceinline__ void set(float* d, const uint32_t* a, uint32_t db) {
    asm volatile("{\n.reg .pred p;\n.reg .b64 db;\nsetp.ne.b32 p, %38, 0;\n"
      "mov.b64 db, {%36, %37};\n"
      "wgmma.mma_async.sync.aligned.m64n64k16.f32.bf16.bf16 {"
      "%0, %1, %2, %3, %4, %5, %6, %7, %8, %9, %10, %11, %12, %13, %14, %15, "
      "%16, %17, %18, %19, %20, %21, %22, %23, %24, %25, %26, %27, %28, %29, %30, %31"
      "}, {%32, %33, %34, %35}, db, p, 1, 1, 1;\n}\n"
      : "=f"(d[0]), "=f"(d[1]), "=f"(d[2]), "=f"(d[3]), "=f"(d[4]), "=f"(d[5]), "=f"(d[6]), "=f"(d[7]),
        "=f"(d[8]), "=f"(d[9]), "=f"(d[10]), "=f"(d[11]), "=f"(d[12]), "=f"(d[13]), "=f"(d[14]), "=f"(d[15]),
        "=f"(d[16]), "=f"(d[17]), "=f"(d[18]), "=f"(d[19]), "=f"(d[20]), "=f"(d[21]), "=f"(d[22]), "=f"(d[23]),
        "=f"(d[24]), "=f"(d[25]), "=f"(d[26]), "=f"(d[27]), "=f"(d[28]), "=f"(d[29]), "=f"(d[30]), "=f"(d[31])
      : "r"(a[0]), "r"(a[1]), "r"(a[2]), "r"(a[3]), "r"(db), "n"(HB), "n"(0));
  }
};
template <> struct WgSST<48> {
  template <uint32_t HA, uint32_t HB>
  static __device__ __forceinline__ void mma(float* d, uint32_t da, uint32_t db, int sc) {
    asm volatile("{\n.reg .pred p;\n.reg .b64 da, db;\nsetp.ne.b32 p, %28, 0;\n"
      "mov.b64 da, {%24, %25};\nmov.b64 db, {%26, %27};\n"
      "wgmma.mma_async.sync.aligned.m64n48k16.f32.bf16.bf16 {"
      "%0, %1, %2, %3, %4, %5, %6, %7, %8, %9, %10, %11, %12, %13, %14, %15, "
      "%16, %17, %18, %19, %20, %21, %22, %23"
      "}, da, db, p, 1, 1, 0, 1;\n}\n"
      : "+f"(d[0]), "+f"(d[1]), "+f"(d[2]), "+f"(d[3]), "+f"(d[4]), "+f"(d[5]), "+f"(d[6]), "+f"(d[7]),
        "+f"(d[8]), "+f"(d[9]), "+f"(d[10]), "+f"(d[11]), "+f"(d[12]), "+f"(d[13]), "+f"(d[14]), "+f"(d[15]),
        "+f"(d[16]), "+f"(d[17]), "+f"(d[18]), "+f"(d[19]), "+f"(d[20]), "+f"(d[21]), "+f"(d[22]), "+f"(d[23])
      : "r"(da), "n"(HA), "r"(db), "n"(HB), "r"(sc));
  }
};
template <> struct WgSST<80> {
  template <uint32_t HA, uint32_t HB>
  static __device__ __forceinline__ void mma(float* d, uint32_t da, uint32_t db, int sc) {
    asm volatile("{\n.reg .pred p;\n.reg .b64 da, db;\nsetp.ne.b32 p, %44, 0;\n"
      "mov.b64 da, {%40, %41};\nmov.b64 db, {%42, %43};\n"
      "wgmma.mma_async.sync.aligned.m64n80k16.f32.bf16.bf16 {"
      "%0, %1, %2, %3, %4, %5, %6, %7, %8, %9, %10, %11, %12, %13, %14, %15, "
      "%16, %17, %18, %19, %20, %21, %22, %23, %24, %25, %26, %27, %28, %29, %30, %31, "
      "%32, %33, %34, %35, %36, %37, %38, %39"
      "}, da, db, p, 1, 1, 0, 1;\n}\n"
      : "+f"(d[0]), "+f"(d[1]), "+f"(d[2]), "+f"(d[3]), "+f"(d[4]), "+f"(d[5]), "+f"(d[6]), "+f"(d[7]),
        "+f"(d[8]), "+f"(d[9]), "+f"(d[10]), "+f"(d[11]), "+f"(d[12]), "+f"(d[13]), "+f"(d[14]), "+f"(d[15]),
        "+f"(d[16]), "+f"(d[17]), "+f"(d[18]), "+f"(d[19]), "+f"(d[20]), "+f"(d[21]), "+f"(d[22]), "+f"(d[23]),
        "+f"(d[24]), "+f"(d[25]), "+f"(d[26]), "+f"(d[27]), "+f"(d[28]), "+f"(d[29]), "+f"(d[30]), "+f"(d[31]),
        "+f"(d[32]), "+f"(d[33]), "+f"(d[34]), "+f"(d[35]), "+f"(d[36]), "+f"(d[37]), "+f"(d[38]), "+f"(d[39])
      : "r"(da), "n"(HA), "r"(db), "n"(HB), "r"(sc));
  }
};
template <> struct WgSST<192> {
  template <uint32_t HA, uint32_t HB>
  static __device__ __forceinline__ void mma(float* d, uint32_t da, uint32_t db, int sc) {
    asm volatile("{\n.reg .pred p;\n.reg .b64 da, db;\nsetp.ne.b32 p, %100, 0;\n"
      "mov.b64 da, {%96, %97};\nmov.b64 db, {%98, %99};\n"
      "wgmma.mma_async.sync.aligned.m64n192k16.f32.bf16.bf16 {"
      "%0, %1, %2, %3, %4, %5, %6, %7, %8, %9, %10, %11, %12, %13, %14, %15, "
      "%16, %17, %18, %19, %20, %21, %22, %23, %24, %25, %26, %27, %28, %29, %30, %31, "
      "%32, %33, %34, %35, %36, %37, %38, %39, %40, %41, %42, %43, %44, %45, %46, %47, "
      "%48, %49, %50, %51, %52, %53, %54, %55, %56, %57, %58, %59, %60, %61, %62, %63, "
      "%64, %65, %66, %67, %68, %69, %70, %71, %72, %73, %74, %75, %76, %77, %78, %79, "
      "%80, %81, %82, %83, %84, %85, %86, %87, %88, %89, %90, %91, %92, %93, %94, %95"
      "}, da, db, p, 1, 1, 0, 1;\n}\n"
      : "+f"(d[0]), "+f"(d[1]), "+f"(d[2]), "+f"(d[3]), "+f"(d[4]), "+f"(d[5]), "+f"(d[6]), "+f"(d[7]),
        "+f"(d[8]), "+f"(d[9]), "+f"(d[10]), "+f"(d[11]), "+f"(d[12]), "+f"(d[13]), "+f"(d[14]), "+f"(d[15]),
        "+f"(d[16]), "+f"(d[17]), "+f"(d[18]), "+f"(d[19]), "+f"(d[20]), "+f"(d[21]), "+f"(d[22]), "+f"(d[23]),
        "+f"(d[24]), "+f"(d[25]), "+f"(d[26]), "+f"(d[27]), "+f"(d[28]), "+f"(d[29]), "+f"(d[30]), "+f"(d[31]),
        "+f"(d[32]), "+f"(d[33]), "+f"(d[34]), "+f"(d[35]), "+f"(d[36]), "+f"(d[37]), "+f"(d[38]), "+f"(d[39]),
        "+f"(d[40]), "+f"(d[41]), "+f"(d[42]), "+f"(d[43]), "+f"(d[44]), "+f"(d[45]), "+f"(d[46]), "+f"(d[47]),
        "+f"(d[48]), "+f"(d[49]), "+f"(d[50]), "+f"(d[51]), "+f"(d[52]), "+f"(d[53]), "+f"(d[54]), "+f"(d[55]),
        "+f"(d[56]), "+f"(d[57]), "+f"(d[58]), "+f"(d[59]), "+f"(d[60]), "+f"(d[61]), "+f"(d[62]), "+f"(d[63]),
        "+f"(d[64]), "+f"(d[65]), "+f"(d[66]), "+f"(d[67]), "+f"(d[68]), "+f"(d[69]), "+f"(d[70]), "+f"(d[71]),
        "+f"(d[72]), "+f"(d[73]), "+f"(d[74]), "+f"(d[75]), "+f"(d[76]), "+f"(d[77]), "+f"(d[78]), "+f"(d[79]),
        "+f"(d[80]), "+f"(d[81]), "+f"(d[82]), "+f"(d[83]), "+f"(d[84]), "+f"(d[85]), "+f"(d[86]), "+f"(d[87]),
        "+f"(d[88]), "+f"(d[89]), "+f"(d[90]), "+f"(d[91]), "+f"(d[92]), "+f"(d[93]), "+f"(d[94]), "+f"(d[95])
      : "r"(da), "n"(HA), "r"(db), "n"(HB), "r"(sc));
  }
};

struct FftConst {
  uint32_t f[2][4], fi[4][4];
  uint32_t ta[2][2], tb[2][2];
};
__device__ __forceinline__ void cis(int m, float scale, float& c, float& s) {
  const float a = (float)m * (-6.283185307179586f * scale);
  c = __cosf(a);
  s = __sinf(a);
}
__device__ __forceinline__ void fft_tables(uint32_t (&v)[12], int tw) {
  const int row = tw >> 2, ch = tw & 3;
#pragma unroll
  for (int i = 0; i < 4; i++) {
    float c[2], s[2], x[2];
#pragma unroll
    for (int e = 0; e < 2; e++) {
      cis((((32 * (8 * ch + 2 * i + e) + 15) * (4 * row - 63) + 2048) & 4095) - 2048, 1.f / 4096, c[e], s[e]);
      float gc, gs;
      cis((((row & 15) * (8 * (ch & 1) + 2 * i + e) + 8) & 15) - 8, 1.f / 16, gc, gs);
      x[e] = (row >> 4) == (ch >> 1) ? gc : (ch >> 1) ? gs : -gs;
    }
    v[i] = pack2(c[0] * 0.125f, c[1] * 0.125f);
    v[4 + i] = pack2(s[0] * 0.125f, s[1] * 0.125f);
    v[8 + i] = pack2(x[0], x[1]);
  }
#pragma unroll
  for (int i = 0; i < 12; i++) asm volatile("" : "+r"(v[i]));
}
__device__ __forceinline__ void fft_tables_store(const uint32_t (&v)[12], uint32_t sb, int tw) {
  const int row = tw >> 2;
  const uint32_t x = ((tw ^ (row >> 1)) & 3) << 4, a = sb + OFF_FT + (16 * (row >> 3) + (row & 7)) * 64 + x;
  sts128(a, v[0], v[1], v[2], v[3]);
  sts128(a + 512, v[4], v[5], v[6], v[7]);
  sts128(sb + OFF_GT + row * 64 + x, v[8], v[9], v[10], v[11]);
}
__device__ __forceinline__ void fft_twiddles(uint32_t (&v)[2], int tw) {
  float a[2], s[2];
#pragma unroll
  for (int i = 0; i < 2; i++) {
    float c;
    cis((2 * (2 * (tw & 3) + i) - 15) * (4 * (tw >> 2) - 63), 1.f / 4096, c, s[i]);
    a[i] = __fdividef(-s[i], 1.f + c);
  }
  v[0] = pack2(a[0], a[1]);
  v[1] = pack2(s[0], s[1]);
  asm volatile("" : "+r"(v[0]), "+r"(v[1]));
}
__device__ __forceinline__ void fft_matrices(FftConst& k, uint32_t sb, int w, int lane) {
  const uint32_t x = (lane >> 1) & 3;
  const uint2 t0 = lds64(sb + OFF_TT + 256 * w + 8 * lane), t1 = lds64(sb + OFF_TT + 256 * w + 8 * (lane ^ 3));
  k.ta[0][0] = t0.x;
  k.tb[0][0] = t0.y;
  k.ta[1][1] = __byte_perm(t1.x, 0, 0x1032);
  k.tb[1][1] = __byte_perm(t1.y, 0, 0x1032);
#pragma unroll
  for (int j = 0; j < 2; j++) {
    k.ta[1 - j][j] = k.ta[j][j] ^ 0x80008000u;
    k.tb[1 - j][j] = k.tb[j][j] ^ 0x80008000u;
    asm volatile("" : "+r"(k.ta[0][j]), "+r"(k.tb[0][j]), "+r"(k.ta[1][j]), "+r"(k.tb[1][j]));
  }
#pragma unroll
  for (int i = 0; i < 2; i++) {
    ldsm4(k.f[i], sb + OFF_FT + (16 * w + (lane & 15)) * 64 + (((2 * i + (lane >> 4)) ^ x) << 4));
    ldsm4t(k.fi[i], sb + OFF_FT + (32 * i + lane) * 64 + ((w ^ x) << 4));
#pragma unroll
    for (int j = 0; j < 4; j++) {
      k.fi[2 + i][j] = (j & 1) ? k.fi[i][j - 1] ^ 0x80008000u : k.fi[i][j + 1];
      asm volatile("" : "+r"(k.fi[2 + i][j]));
    }
  }
}
__device__ __forceinline__ void rot(uint32_t& x, uint32_t& y, uint32_t a, uint32_t b) {
  x = bfma(a, y, x);
  y = bfma(b, x, y);
  x = bfma(a, y, x);
}
__device__ __forceinline__ void twiddle_fwd(uint32_t (&a)[4][4], float* d, const FftConst& k) {
#pragma unroll
  for (int q = 0; q < 4; q++)
#pragma unroll
    for (int j = 0; j < 2; j++) {
      const float* x = d + 8 * q + 4 * j;
      uint32_t re = pack2(x[0], x[1]), im = pack2(x[2], x[3]);
      rot(re, im, k.ta[0][j], k.tb[0][j]);
      a[q & 2][2 * j + (q & 1)] = re;
      a[(q & 2) + 1][2 * j + (q & 1)] = im;
    }
}
__device__ __forceinline__ void g_step(float* d, const uint32_t (&a)[4][4], uint32_t dre, uint32_t dim) {
  WgRS<32>::set<HI_SW64>(d, a[0], dre);
  WgRS<32>::set<HI_SW64>(d + 16, a[2], dre);
  WgRS<32>::mma<HI_SW64>(d, a[1], dim);
  WgRS<32>::mma<HI_SW64>(d + 16, a[3], dim);
  wg_commit();
}

__device__ __forceinline__ void products(uint32_t (&a)[4][4], const float* H, const float* U, int p) {
#pragma unroll
  for (int j = 0; j < 2; j++)
#pragma unroll
    for (int m = 2 * p; m < 2 * p + 2; m++) {
      float pr[2], pi[2];
#pragma unroll
      for (int x = 0; x < 2; x++)
#pragma unroll
        for (int q = 0; q <= m; q++) {
          const int ih = 16 * (q >> 1) + 2 * (q & 1) + 4 * j + x, iu = 16 * ((m - q) >> 1) + 2 * ((m - q) & 1) + 4 * j + x;
          pr[x] = q ? fmaf(H[ih], U[iu], pr[x]) : H[ih] * U[iu];
          pi[x] = q ? fmaf(H[ih], U[iu + 8], pi[x]) : H[ih] * U[iu + 8];
          pr[x] = fmaf(-H[ih + 8], U[iu + 8], pr[x]);
          pi[x] = fmaf(H[ih + 8], U[iu], pi[x]);
        }
      a[m & 2][2 * j + (m & 1)] = pack2(pr[0], pr[1]);
      a[(m & 2) + 1][2 * j + (m & 1)] = pack2(pi[0], pi[1]);
    }
}

__device__ __forceinline__ void conv_channel(const FftConst& k, uint32_t sb, int c, int wg, int w, int lane) {
  const uint32_t cb = sb + off_ch(c), bars = sb + OFF_BAR;
  const uint32_t du = desc_lo(cb, 1024), dg = desc_lo(sb + OFF_GT, 16), dz = desc_lo(cb + U_BYTES, 16);
  float U[32], H[32];
  uint32_t a[4][4], e[4][4];
  const float dv = __uint_as_float(lds32(sb + OFF_D + 4 * c));
  wg_fence();
  WgRS<64>::set<HI_SW32>(H, k.f[0], du + 256);
  WgRS<64>::mma<HI_SW32>(H, k.f[1], du + 256 + 32);
  wg_commit();
  wg_wait<0>();
  pin<32>(H);
  twiddle_fwd(a, H, k);
  mbar_wait(bars + 8 * (B_U + (c < 3 ? c : 3)), 0);
  TSM(w == 0 && c < 3, 7 + wg);
  wg_fence();
  WgRS<64>::set<HI_SW32>(U, k.f[0], du);
  WgRS<64>::mma<HI_SW32>(U, k.f[1], du + 32);
  wg_commit();
  g_step(H, a, dg, dg + 64);
  wg_wait<1>();
  pin<32>(U);
  twiddle_fwd(e, U, k);
  wg_fence();
  g_step(U, e, dg, dg + 64);
  wg_wait<0>();
  pin<32>(U);
  pin<32>(H);
#pragma unroll
  for (int j = 0; j < 4; j++) H[4 * (j >> 1) + (j & 1)] += dv;
  float V[32];
#pragma unroll
  for (int p = 0; p < 2; p++) {
    products(a, H, U, p);
    wg_fence();
    WgRS<32>::set<HI_SW64>(V + 16 * p, a[2 * p], dg + 64);
    WgRS<32>::mma<HI_SW64>(V + 16 * p, a[2 * p + 1], dg);
    wg_commit();
  }
  const uint32_t za = cb + U_BYTES + (8 * w + (lane & 7)) * 128 + (((lane >> 3) ^ (lane & 7)) << 4);
  const uint32_t ya = cb + (lane >> 4) * 1024 + (8 * w + (lane & 7)) * 32 + ((((lane >> 3) ^ (lane >> 2)) & 1) << 4);
  wg_sync(1 + wg);
#pragma unroll
  for (int p = 0; p < 2; p++) {
    if (p == 0) wg_wait<1>();
    else wg_wait<0>();
    pin<16>(V + 16 * p);
#pragma unroll
    for (int i = 0; i < 4; i++) {
      const int j = i & 1;
      const float* x = V + 16 * p + 4 * j + (i & 2);
      e[p][i] = pack2(x[8], x[9]);
      e[2 + p][i] = pack2(x[0], x[1]);
      rot(e[p][i], e[2 + p][i], k.ta[1][j], k.tb[1][j]);
    }
    stsm4(za ^ (64 * p), e[p]);
    stsm4((za ^ (64 * p)) + 4096, e[2 + p]);
  }
  fence_async_smem();
  wg_sync(1 + wg);
  wg_fence();
  WgRS<64>::set<HI_SW128>(H, k.fi[0], dz);
#pragma unroll
  for (int ks = 1; ks < 4; ks++) WgRS<64>::mma<HI_SW128>(H, k.fi[ks], dz + 128 * ks);
  wg_commit();
  wg_wait<0>();
  pin<32>(H);
  if (lane == 0) mbar_arrive(bars + 8 * B_CVD);
  TSIF(w == 0, 88 + c);
#pragma unroll
  for (int j = 0; j < 8; j++)
    a[j >> 2][j & 3] = j < 2 ? pack2(H[4 * j], H[4 * j + 1]) : pack2(H[4 * j] + H[4 * j - 6], H[4 * j + 1] + H[4 * j - 5]);
  stsm4(ya, a[0]);
  stsm4(ya + 2048, a[1]);
  fence_async_smem();
  __syncwarp();
}

__device__ __forceinline__ void prep_slab(uint4* res, const uint2* sw, uint32_t sb, int slab, int w, int lane) {
  const int t = lane & 3, tp = (lane & 7) >> 1, pos = 8 * tp + 2 * (((lane >> 3) + tp) & 3) + (lane & 1);
  const uint32_t base = sb + OFF_KVS + slab * KVS_BYTES + pos * 128;
  uint32_t kk[2][4][4], vv[2][4];
  mbar_wait(sb + OFF_BAR + 8 * (B_KV + slab), 0);
#pragma unroll
  for (int h = 0; h < 2; h++) {
#pragma unroll
    for (int j = 0; j < 4; j++) {
      const uint32_t a = base + 128 * j;
      ldsm4t(kk[h][j], a + (((w + 4 * h) ^ ((a >> 7) & 7)) << 4));
    }
    const uint32_t a = base + KVS_V;
    ldsm4t(vv[h], a + (((w + 4 * h) ^ ((a >> 7) & 7)) << 4));
  }
#pragma unroll
  for (int h = 0; h < 2; h++) {
    uint32_t (&k)[4][4] = kk[h];
    uint32_t (&v)[4] = vv[h];
    const uint32_t w0 = __byte_perm(sw[h].x, 0, 0x1010), w1 = __byte_perm(sw[h].x, 0, 0x3232);
    const uint32_t w2 = __byte_perm(sw[h].y, 0, 0x1010), w3 = __byte_perm(sw[h].y, 0, 0x3232);
#pragma unroll
    for (int m = 0; m < 4; m++)
      v[m] = bmul(badd(badd(badd(bmul(k[0][m], w3), bmul(k[1][m], w2)), bmul(k[2][m], w1)), bmul(k[3][m], w0)), v[m]);
    uint32_t a[4];
#pragma unroll
    for (int m = 0; m < 4; m++) a[m] = (t & 1) ? v[(m + 3) & 3] : v[m];
    res[h] = (t & 2) ? make_uint4(a[2], a[3], a[0], a[1]) : make_uint4(a[0], a[1], a[2], a[3]);
  }
}

__device__ __forceinline__ void prep_gate(const Params& p, uint32_t sb, int b, int w, int lane) {
  uint2 gw[5], x[4][5];
#pragma unroll
  for (int j = 0; j < 5; j++) gw[j] = ldg64(reinterpret_cast<const uint2*>(p.gate_w) + lane + 32 * j);
#pragma unroll
  for (int i = 0; i < 4; i++)
#pragma unroll
    for (int j = 0; j < 5; j++)
      x[i][j] = ldg64(reinterpret_cast<const uint2*>(p.q) + (16 * b + 4 * w + i) * (DIM / 4) + lane + 32 * j);
  float s[4];
#pragma unroll
  for (int i = 0; i < 4; i++) {
    s[i] = 0.f;
#pragma unroll
    for (int j = 0; j < 5; j++) {
      const uint32_t m0 = bmul(x[i][j].x, gw[j].x), m1 = bmul(x[i][j].y, gw[j].y);
      s[i] += (bf_lo(m0) + bf_hi(m0)) + (bf_lo(m1) + bf_hi(m1));
    }
  }
  const bool h = lane & 16, q = lane & 8;
  const float a = (h ? s[2] : s[0]) + __shfl_xor_sync(0xffffffffu, h ? s[0] : s[2], 16);
  const float c = (h ? s[3] : s[1]) + __shfl_xor_sync(0xffffffffu, h ? s[1] : s[3], 16);
  float z = (q ? c : a) + __shfl_xor_sync(0xffffffffu, q ? a : c, 8);
#pragma unroll
  for (int o = 4; o > 0; o >>= 1) z += __shfl_xor_sync(0xffffffffu, z, o);
  z = bf_lo(pack2(z, 0.f));
  z = bf_lo(pack2(__fdividef(1.f, 1.f + __expf(-z)), 0.f));
  mbar_wait(sb + OFF_BAR + 8 * B_S3, 0);
  if ((lane & 7) == 0) asm volatile("st.shared.f32 [%0], %1;" ::"r"(sb + OFF_GATE + 64 * (b & 7) + 16 * w + (lane >> 1)), "f"(z) : "memory");
  fence_async_smem();
}

__device__ __forceinline__ uint32_t bmax(uint32_t a, uint32_t b) {
  uint32_t d;
  asm("max.bf16x2 %0, %1, %2;" : "=r"(d) : "r"(a), "r"(b));
  return d;
}
__device__ __forceinline__ void softmax_two(const float (&l)[2][2], uint32_t& p0, uint32_t& p1) {
  constexpr float kScale = 0.22360679774997896f, kLog2e = 1.4426950408889634f;
  const uint32_t r0 = pack2(l[0][0], l[1][0]), r1 = pack2(l[0][1], l[1][1]);
  const uint32_t x0 = pack2(bf_lo(r0) * kScale, bf_hi(r0) * kScale), x1 = pack2(bf_lo(r1) * kScale, bf_hi(r1) * kScale);
  uint32_t m = bmax(x0, x1);
  m = bmax(m, __shfl_xor_sync(0xffffffffu, m, 1));
  m = bmax(m, __shfl_xor_sync(0xffffffffu, m, 2));
  const float m0 = bf_lo(m) * kLog2e, m1 = bf_hi(m) * kLog2e;
  p0 = pack2(ex2(bf_lo(x0) * kLog2e - m0), ex2(bf_lo(x1) * kLog2e - m0));
  p1 = pack2(ex2(bf_hi(x0) * kLog2e - m1), ex2(bf_hi(x1) * kLog2e - m1));
}

__device__ __forceinline__ void halo_read(uint32_t (&kpv)[10], uint32_t (&vpv)[10], uint32_t (&tg)[7], const uint4* hp) {
#pragma unroll
  for (int j = 0; j < 7; j++) {
    uint32_t x0, x1, x2;
    asm volatile("ld.relaxed.gpu.global.v4.u32 {%0, %1, %2, %3}, [%4];"
                 : "=r"(x0), "=r"(x1), "=r"(x2), "=r"(tg[j]) : "l"(hp + 32 * j) : "memory");
    if (j < 4) kpv[3 * j] = x0; else vpv[3 * j - 10] = x0;
    if (j < 3) kpv[3 * j + 1] = x1; else vpv[3 * j - 9] = x1;
    if (j < 3) kpv[3 * j + 2] = x2; else if (j < 6) vpv[3 * j - 8] = x2;
  }
}

template <int ROT>
__device__ __forceinline__ void pack_qkv(const float* acc, uint32_t (&qlo)[10], uint32_t (&qhi)[10], uint32_t (&klo)[10],
                                         uint32_t (&khi)[10], uint32_t (&vlo)[10], uint32_t (&vhi)[10]) {
#pragma unroll
  for (int j = 0; j < 10; j++) {
    const int x = (j + ROT) % 10, tq = x < 8 ? x : 16 + x, tk = x < 8 ? 8 + x : 18 + x, tv = x < 8 ? 16 + x : 20 + x;
    khi[j] = pack2(acc[4 * tk + 2], acc[4 * tk + 3]);
    vhi[j] = movm(pack2(acc[4 * tv + 2], acc[4 * tv + 3]));
    qlo[j] = pack2(acc[4 * tq], acc[4 * tq + 1]);
    qhi[j] = pack2(acc[4 * tq + 2], acc[4 * tq + 3]);
    klo[j] = pack2(acc[4 * tk], acc[4 * tk + 1]);
    vlo[j] = pack2(acc[4 * tv], acc[4 * tv + 1]);
    asm volatile("" : "+r"(khi[j]), "+r"(qlo[j]), "+r"(qhi[j]), "+r"(klo[j]), "+r"(vlo[j]));
  }
}

template <int ROT> __device__ __forceinline__ void halo_send(const float* acc, uint4* ho, uint32_t tag) {
#pragma unroll
  for (int j = 0; j < 7; j++) {
    uint32_t x[3];
#pragma unroll
    for (int e = 0; e < 3; e++) {
      const int i = 3 * j + e, y = (i % 10 + ROT) % 10, tk = y < 8 ? 8 + y : 18 + y, tv = y < 8 ? 16 + y : 20 + y;
      x[e] = i < 10 ? pack2(acc[4 * tk + 2], acc[4 * tk + 3]) : i < 20 ? movm(pack2(acc[4 * tv + 2], acc[4 * tv + 3])) : 0u;
    }
    asm volatile("st.relaxed.gpu.global.v4.u32 [%0], {%1, %2, %3, %4};" ::"l"(ho + 32 * j), "r"(x[0]), "r"(x[1]), "r"(x[2]), "r"(tag) : "memory");
  }
}

__device__ __forceinline__ void attention(float* acc, uint32_t sb, int b, int par, int w, int lane, uint32_t tag) {
  const int g = lane >> 2, t = lane & 3;
  uint32_t klo[10], khi[10], vlo[10], vhi[10], qlo[10], qhi[10], kpv[10], vpv[10];
  if (w == 3 && b < NCTA - 8) {
    uint4* ho = g_halo + (b * 2 + par) * 224 + lane;
    if (tail_first(b & 7)) halo_send<8>(acc, ho, tag);
    else halo_send<0>(acc, ho, tag);
    TSIF(par == 0, 76);
    pin<120>(acc);
  }
  if (tail_first(b & 7)) pack_qkv<8>(acc, qlo, qhi, klo, khi, vlo, vhi);
  else pack_qkv<0>(acc, qlo, qhi, klo, khi, vlo, vhi);
  const uint32_t xa = sb + OFF_KVX + (par * 3) * 2560 + lane * 16;
  if (w < 3) {
    sts128(xa + w * 2560, khi[0], khi[1], khi[2], khi[3]);
    sts128(xa + w * 2560 + 512, khi[4], khi[5], khi[6], khi[7]);
    sts128(xa + w * 2560 + 1024, khi[8], khi[9], vhi[0], vhi[1]);
    sts128(xa + w * 2560 + 1536, vhi[2], vhi[3], vhi[4], vhi[5]);
    sts128(xa + w * 2560 + 2048, vhi[6], vhi[7], vhi[8], vhi[9]);
  }
  TSIF(par == 0 && w == 1, 64);
#pragma unroll
  for (int j = 0; j < 10; j++) vlo[j] = movm(vlo[j]);
  const bool far0 = 2 * t > g, far1 = 2 * t + 1 > g;
  const uint32_t mfar = (far0 ? 0x0000FFFFu : 0u) | (far1 ? 0xFFFF0000u : 0u);
  float slo[4][2], lg[2][2];
  uint32_t phi[4], plo[4], qml[4], qmh[4];
#pragma unroll
  for (int h = 0; h < 4; h++) {
    const int f = h == 0 ? 0 : h == 1 ? 3 : h == 2 ? 5 : 8, hf = h < 2 ? 2 : 7;
    const bool mine = (h & 1) ? t >= 2 : t < 2;
    qml[h] = mine ? qlo[hf] : 0u;
    qmh[h] = mine ? qhi[hf] : 0u;
    float a[4] = {0.f, 0.f, 0.f, 0.f}, c[4] = {0.f, 0.f, 0.f, 0.f};
    mma16816(a, qlo[f], qhi[f], qlo[f + 1], qhi[f + 1], klo[f], klo[f + 1]);
    mma16816(c, qlo[f], qhi[f], qlo[f + 1], qhi[f + 1], khi[f], khi[f + 1]);
    mma1688(a, qml[h], qmh[h], klo[hf]);
    mma1688(c, qml[h], qmh[h], khi[hf]);
    slo[h][0] = a[0];
    slo[h][1] = a[1];
    lg[h & 1][0] = far0 ? a[2] : c[2];
    lg[h & 1][1] = far1 ? a[3] : c[3];
    if (h & 1) softmax_two(lg, phi[h - 1], phi[h]);
  }
  TSIF(par == 0 && w == 1, 65);
  wg_sync(1 + par);
  TSIF(par == 0 && w == 1, 66);
  const bool nohist = (w == 0) && (b < 8);
  const uint4* hp = g_halo + ((b - 8) * 2 + par) * 224 + lane;
  uint32_t tg[7];
  if (w > 0) {
    const uint4 v0 = lds128(xa + (w - 1) * 2560), v1 = lds128(xa + (w - 1) * 2560 + 512), v2 = lds128(xa + (w - 1) * 2560 + 1024);
    const uint4 v3 = lds128(xa + (w - 1) * 2560 + 1536), v4 = lds128(xa + (w - 1) * 2560 + 2048);
    kpv[0] = v0.x; kpv[1] = v0.y; kpv[2] = v0.z; kpv[3] = v0.w; kpv[4] = v1.x; kpv[5] = v1.y; kpv[6] = v1.z; kpv[7] = v1.w;
    kpv[8] = v2.x; kpv[9] = v2.y; vpv[0] = v2.z; vpv[1] = v2.w; vpv[2] = v3.x; vpv[3] = v3.y; vpv[4] = v3.z; vpv[5] = v3.w;
    vpv[6] = v4.x; vpv[7] = v4.y; vpv[8] = v4.z; vpv[9] = v4.w;
  } else if (nohist) {
#pragma unroll
    for (int j = 0; j < 10; j++) kpv[j] = vpv[j] = 0u;
  } else {
    TSIF(par == 0, 77);
    halo_read(kpv, vpv, tg, hp);
  }
  if (w == 0 && !nohist) {
    int spins = 0;
    while (true) {
      bool ok = true;
#pragma unroll
      for (int j = 0; j < 7; j++) ok = ok && tg[j] == tag;
      if (__all_sync(0xffffffffu, ok) || ++spins > SPIN_LIMIT) break;
      halo_read(kpv, vpv, tg, hp);
    }
    TSIF(par == 0, 79);
  }
#pragma unroll
  for (int h = 0; h < 4; h++) {
    const int f = h == 0 ? 0 : h == 1 ? 3 : h == 2 ? 5 : 8, hf = h < 2 ? 2 : 7;
    float a[4] = {0.f, 0.f, 0.f, 0.f};
    mma16816(a, qlo[f], qhi[f], qlo[f + 1], qhi[f + 1], kpv[f], kpv[f + 1]);
    mma1688(a, qml[h], qmh[h], kpv[hf]);
    const float ninf = __int_as_float(0xff800000);
    lg[h & 1][0] = far0 ? (nohist ? ninf : a[0]) : slo[h][0];
    lg[h & 1][1] = far1 ? (nohist ? ninf : a[1]) : slo[h][1];
    if (h & 1) softmax_two(lg, plo[h - 1], plo[h]);
  }
  TSIF(par == 0 && w <= 1, 67 + w);
  uint32_t ov[20];
#pragma unroll
  for (int hp = 0; hp < 2; hp++) {
    const int hf = hp ? 7 : 2;
    float sh[4] = {0.f, 0.f, 0.f, 0.f}, i0 = 0.f, i1 = 0.f;
#pragma unroll
    for (int e = 0; e < 2; e++) {
      const int h = 2 * hp + e, f = h == 0 ? 0 : h == 1 ? 3 : h == 2 ? 5 : 8;
      const uint32_t a0 = plo[h] & mfar, a2 = plo[h] & ~mfar, a3 = phi[h] & mfar, c1 = phi[h] & ~mfar;
      float sum[4] = {0.f, 0.f, 0.f, 0.f};
      mma1688(sum, plo[h], phi[h], 0x3F803F80u);
      const float r0 = rcp(sum[0]), r1 = rcp(sum[2]);
#pragma unroll
      for (int j = f; j < f + 2; j++) {
        float o[4] = {0.f, 0.f, 0.f, 0.f};
        mma16816(o, a0, 0u, a2, a3, vpv[j], vlo[j]);
        mma1688(o, 0u, c1, vhi[j]);
        ov[2 * j] = pack2(o[0] * r0, o[1] * r0);
        ov[2 * j + 1] = pack2(o[2] * r1, o[3] * r1);
      }
      const bool mine = e ? g >= 4 : g < 4;
      mma16816(sh, a0, 0u, a2, a3, mine ? vpv[hf] : 0u, mine ? vlo[hf] : 0u);
      mma1688(sh, 0u, c1, mine ? vhi[hf] : 0u);
      if (e == 0 || t >= 2) {
        i0 = r0;
        i1 = r1;
      }
    }
    ov[2 * hf] = pack2(sh[0] * i0, sh[1] * i0);
    ov[2 * hf + 1] = pack2(sh[2] * i1, sh[3] * i1);
  }
  TS(32 + 4 * par + w);
  mbar_wait(sb + OFF_BAR + 8 * B_P1, 0);
  const uint32_t oa = sb + OFF_OA + (lane >> 4) * 2048 + (32 * w + 2 * (lane & 15) + par) * 16;
#pragma unroll
  for (int j = 0; j < 5; j++) stsm4(oa + 4096 * j, ov + 4 * j);
  TSIF(par == 0 && w == 0, 120);
  fence_async_smem();
  TSIF(par == 0 && w == 0, 121);
  __syncwarp();
  if (lane == 0) mbar_arrive(sb + OFF_BAR + 8 * B_ATTN);
  TSM(w == 0 || w == 2, 122 + par + (w == 2 ? 3 : 0));
}

struct Maps {
  CUtensorMap x, wm, wt, k, v, y, wo, qm, qt, om, ot;
};

__device__ __forceinline__ void load_stage(uint32_t sb, int kb, int b, const Maps& m) {
  const uint32_t st = sb + (kb & 3) * STAGE_BYTES, bar = sb + OFF_BAR + 8 * (B_FULL1 + (kb & 3));
  const int r = b >> 3, hg = b & 7, slab = kb - KV_KB;
  const bool kv = slab >= 0 && slab < 5;
  const uint32_t kbar = sb + OFF_BAR + 8 * (B_KV + slab), dst = sb + OFF_KVS + slab * KVS_BYTES;
  mbar_expect_tx(bar, STAGE_BYTES);
  if (kv) mbar_expect_tx(kbar, KVS_BYTES);
  tma_3d(st, &m.x, 64 * kb, 64 * r, 0, bar);
  tma_3d(st + ST_W, &m.wm, 80 * hg + (tail_first(hg) ? 16 : 0), 64 * kb, 0, bar);
  tma_3d(st + ST_WT, &m.wt, 80 * hg + (tail_first(hg) ? 0 : 64), 64 * kb, 0, bar);
  if (kv) tma_3d(dst, &m.k, 0, 32 * (b >> 1) - 3, 2 * slab + (b & 1), kbar);
  if (kv) tma_3d(dst + KVS_V, &m.v, 0, 32 * (b >> 1), 2 * slab + (b & 1), kbar);
}

__global__ void __launch_bounds__(NTHR, 1) fused_kernel(const __grid_constant__ Maps m, const Params p) {
  extern __shared__ __align__(1024) uint8_t smem[];
  const uint32_t sb = (uint32_t)__cvta_generic_to_shared(smem);
  const uint32_t bars = sb + OFF_BAR;
  const int tid = threadIdx.x, lane = tid & 31;
  int b = blockIdx.x;
  b = (((b & 63) >> 3) * 2 + (b & 1)) * 8 + (((b < 64 ? 0x6521 : 0x7430) >> (4 * ((b >> 1) & 3))) & 7);
  const int r = b >> 3, hg = b & 7;

  if (tid == T_ISSUE) {
    TSM(true, 0);
    mbar_init(bars + 8 * B_F0, 1);
    fence_async_smem();
    mbar_expect_tx(bars + 8 * B_F0, T_ISS2 ? ST_W : ST_WT);
    tma_3d(sb, &m.x, 0, 64 * r, 0, bars + 8 * B_F0);
    if (!T_ISS2) tma_3d(sb + ST_W, &m.wm, 80 * hg + (tail_first(hg) ? 16 : 0), 0, 0, bars + 8 * B_F0);
#pragma unroll
    for (int i = 0; i < 4; i++) mbar_init(bars + 8 * (B_FULL1 + i), 1);
    fence_async_smem();
    mbar_expect_tx(bars + 8 * B_FULL1, STAGE_BYTES - ST_WT);
    tma_3d(sb + ST_WT, &m.wt, 80 * hg + (tail_first(hg) ? 0 : 64), 0, 0, bars + 8 * B_FULL1);
    load_stage(sb, 1, b, m);
  } else if (T_ISS2 && tid == T_ISS2) {
    mbar_init(bars + 8 * B_F1, 1);
    fence_async_smem();
    mbar_expect_tx(bars + 8 * B_F1, ST_WT - ST_W);
    tma_3d(sb + ST_W, &m.wm, 80 * hg + (tail_first(hg) ? 16 : 0), 0, 0, bars + 8 * B_F1);
  } else if (tid == T_INIT) {
#pragma unroll
    for (int i = 0; i < B_F0; i++) mbar_init(bars + 8 * i, i < B_GATE ? 8 : i < B_CVD ? 4 : i == B_CVD ? 20 : 1);
    fence_async_smem();
  }
  const int warp = __shfl_sync(0xffffffffu, tid >> 5, 0), wg = warp >> 2, w = warp & 3;
  __syncthreads();

  if (wg == 3) {
    asm volatile("setmaxnreg.dec.sync.aligned.u32 56;");
    if (w == 0) {
      if (lane == 0) {
#pragma unroll 1
        for (int kb = 2; kb < 10; kb++) {
          if (kb >= 4) mbar_wait(bars + 8 * (kb == 7 ? B_E3 : B_EMPTY1 + (kb & 3)), (kb >> 3) & 1);
          TSIF(kb >= 4, 44 + kb);
          load_stage(sb, kb, b, m);
          TSIF(kb == 3, 60);
          if (kb == TRIG_KB) mbar_arrive(bars + 8 * B_LAST);
        }
        mbar_wait(bars + 8 * B_WOP, 0);
        mbar_wait(bars + 8 * WL_TRIG, 0);
        mbar_wait(bars + 8 * B_EPOCH, 0);
        flag_wait(g_cnt + C_W + 32 * hg, (lds32(sb + OFF_EPOCH) + 1) * 16);
        TS(30);
#pragma unroll 1
        for (int j = 0; j < 8; j++) {
          if (j >= 6) mbar_wait(bars + 8 * (B_EMPTY2 + j - 6), 0);
          if (j == 4) mbar_wait(bars + 8 * B_ATTN, 0);
          TSIF(j >= 6, 100 + j);
          mbar_expect_tx(bars + 8 * (B_FULL2 + j), j == 0 ? WO_BYTES : j == 5 ? O_BYTES + WO_BYTES + 512 : O_BYTES + WO_BYTES);
          bulk_load(sb + off_w(j), g_WO + (hg * 8 + step_src(hg, j)) * 800, WO_BYTES, bars + 8 * (B_FULL2 + j));
        }
        mbar_wait(bars + 8 * (B_EMPTY2 + 3), 0);
        mbar_expect_tx(bars + 8 * B_QF, O_BYTES);
        tma_2d(sb + OFF_QS, &m.qm, 80 * hg, 128 * r, bars + 8 * B_QF);
        tma_2d(sb + OFF_QT, &m.qt, 80 * hg + 64, 128 * r, bars + 8 * B_QF);
      }
    } else if (w == 1) {
      unsigned epoch = 0;
      if (lane == 0) {
        epoch = atomicAdd(g_cnt + C_LAUNCH, 1u) / NCTA;
        asm volatile("st.shared.u32 [%0], %1;" ::"r"(sb + OFF_EPOCH), "r"(epoch) : "memory");
        mbar_arrive(bars + 8 * B_EPOCH);
        mbar_wait(bars + 8 * B_KVD, 0);
        mbar_expect_tx(bars + 8 * B_HB, 5 * 4096);
#pragma unroll 1
        for (int c = 0; c < 5; c++) {
          if (c == 3) mbar_wait(bars + 8 * B_S3, 0);
          bulk_load(sb + off_ch(c) + U_BYTES, p.ssm_k + (5 * b + c) * SEQ, 4096, bars + 8 * B_HB);
        }
#pragma unroll
        for (int c = 0; c < 4; c++) mbar_expect_tx(bars + 8 * (B_U + c), c < 3 ? U_BYTES : 2 * U_BYTES);
        const uint4* usrc = g_U + 5 * b * U_PITCH;
        mbar_wait(bars + 8 * B_USIG, 0);
        flag_wait(g_cnt + C_PREP + 32 * (b & 15), (epoch + 1) * NCTA);
        TS(23);
#pragma unroll
        for (int c = 0; c < 5; c++) {
          if (c == 3) mbar_wait(bars + 8 * (B_U + 2), 0);
          bulk_load(sb + off_ch(c), usrc + c * U_PITCH, U_BYTES, bars + 8 * (B_U + (c < 3 ? c : 3)));
          TSIF(c == 0 || c == 4, 116 + (c >> 2));
        }
      }
      epoch = __shfl_sync(0xffffffffu, epoch, 0);
      if (lane < 8) {
        const int src = (b & ~7) | step_src(hg, lane);
        mbar_wait(bars + 8 * B_ATTN, 0);
        TS(20);
        bool seen = false;
#pragma unroll 1
        for (int spins = 0; spins < SPIN_LIMIT; spins++) {
          const bool now = !seen && (int)(flag_read(g_cnt + C_O + 32 * src) - (epoch + 1)) >= 0;
          if (now && lane >= 1 && lane < 4) bulk_load(sb + off_o(lane), g_O + src * 1280, O_BYTES, bars + 8 * (B_FULL2 + lane));
          seen = seen || now;
          if (__all_sync(0xff, seen)) break;
        }
        TS(21);
        if (lane == 5) bulk_load(sb + OFF_GATE, g_gate + 128 * r, 512, bars + 8 * (B_FULL2 + 5));
#pragma unroll 1
        for (int j = 4; j < 8; j++) {
          if (lane == j) {
            mbar_wait(bars + 8 * (j < 6 ? B_C34 : B_EMPTY2 + j - 6), 0);
            bulk_load(sb + off_o(j), g_O + src * 1280, O_BYTES, bars + 8 * (B_FULL2 + j));
          }
          __syncwarp(0xff);
        }
        TS(22);
      }
    } else if (w == 2) {
      mbar_wait(bars + 8 * B_PREP, 0);
      flag_signal(g_cnt + C_PREP, 16, lane);
      TS(25);
      if (lane == 0) {
        mbar_arrive(bars + 8 * B_USIG);
        mbar_expect_tx(bars + 8 * B_ORB, O_BYTES + 64);
        mbar_wait(bars + 8 * B_GATE, 0);
        publish(g_gate + 16 * b, sb + OFF_GATE + 64 * hg, 64, bars + 8 * B_ORB);
        mbar_wait(bars + 8 * B_ATTN, 0);
        publish(g_O + b * 1280, sb + OFF_OA, O_BYTES, bars + 8 * B_ORB);
        TS(74);
        mbar_wait(bars + 8 * B_ORB, 0);
        flag_bump(g_cnt + C_O + 32 * b);
        TS(26);
        mbar_arrive(bars + 8 * B_OSIG);
      }
    } else {
      if (lane == 0) {
        uint4* dst = g_WO + (hg * 8 + (r >> 1)) * 800 + (r & 1) * 80;
        mbar_wait(bars + 8 * B_S3, 0);
        asm volatile("cp.async.bulk.prefetch.L2.global [%0], 6400;" ::"l"(p.wo + b * 3200) : "memory");
        mbar_wait(bars + 8 * B_P1, 0);
        mbar_wait(bars + 8 * WB_TRIG, 0);
        mbar_expect_tx(bars + 8 * B_WST, WO_BYTES / 2);
        tma_3d(sb + OFF_WA, &m.wo, 0, 40 * r, 5 * hg, bars + 8 * B_WST);
        mbar_wait(bars + 8 * B_WST, 0);
#pragma unroll 1
        for (int n = 0; n < 5; n++) bulk_store(dst + 160 * n, sb + OFF_WA + 1280 * n, 1280);
        bulk_wait_read();
        mbar_expect_tx(bars + 8 * B_WST, WO_BYTES / 2);
#pragma unroll 1
        for (int n = 0; n < 5; n++) bulk_load(sb + OFF_WA + 1280 * n, dst + 160 * n, 1280, bars + 8 * B_WST);
        mbar_wait(bars + 8 * B_WST, 1);
        flag_bump(g_cnt + C_W + 32 * hg);
        mbar_arrive(bars + 8 * B_WOP);
        TS(71);
        mbar_expect_tx(bars + 8 * B_C34, 3 * U_BYTES);
        mbar_expect_tx(bars + 8 * B_YRB, 2 * U_BYTES);
#pragma unroll 1
        for (int c = 0; c < 5; c++) {
          mbar_wait(bars + 8 * (B_YST + c), 0);
          publish(g_U + (5 * b + c) * U_PITCH, sb + off_ch(c), U_BYTES, bars + 8 * (c < 3 ? B_C34 : B_YRB));
        }
        TS(75);
        mbar_wait(bars + 8 * B_C34, 0);
        mbar_wait(bars + 8 * B_YRB, 0);
        flag_bump(g_cnt + C_Y + 32 * (b >> 4));
        TS(27);
        mbar_arrive(bars + 8 * B_YSIG);
        mbar_expect_tx(bars + 8 * B_YFULL, 20480);
        flag_wait(g_cnt + C_Y + 32 * hg, (lds32(sb + OFF_EPOCH) + 1) * 16);
        TS(24);
        tma_2d(sb + OFF_YT, &m.y, 128 * r, 80 * hg, bars + 8 * B_YFULL);
        tma_2d(sb + OFF_YT + 10240, &m.y, 128 * r + 64, 80 * hg, bars + 8 * B_YFULL);
      }
    }
  } else {
    asm volatile("setmaxnreg.inc.sync.aligned.u32 152;");
    if (wg < 2) {
      float acc[120];
#pragma unroll
      for (int i = 0; i < 120; i++) acc[i] = 0.f;
      const uint32_t da = desc_lo(sb + wg * 8192, 16), db = desc_lo(sb + ST_W, 8192), dc = desc_lo(sb + ST_WT, 2048);
      mbar_wait(bars + 8 * B_F0, 0);
      if (T_ISS2) mbar_wait(bars + 8 * B_F1, 0);
      TSIF(w == 0 && wg == 0, 1);
      wg_fence();
#pragma unroll
      for (int k = 0; k < 4; k++) WgSST<192>::mma<HI_SW128, HI_SW128>(acc, da + 2 * k, db + 128 * k, 1);
      wg_commit();
      mbar_wait(bars + 8 * B_FULL1, 0);
      wg_fence();
#pragma unroll
      for (int k = 0; k < 4; k++) WgSST<48>::mma<HI_SW128, HI_SW32>(acc + 96, da + 2 * k, dc + 32 * k, 1);
      wg_commit();
#pragma unroll 1
      for (int kb = 1; kb < 10; kb++) {
        mbar_wait(bars + 8 * (B_FULL1 + (kb & 3)), (kb >> 2) & 1);
        const uint32_t so = (kb & 3) * (STAGE_BYTES >> 4);
        wg_fence();
#pragma unroll
        for (int k = 0; k < 4; k++) {
          WgSST<192>::mma<HI_SW128, HI_SW128>(acc, da + so + 2 * k, db + so + 128 * k, 1);
          WgSST<48>::mma<HI_SW128, HI_SW32>(acc + 96, da + so + 2 * k, dc + so + 32 * k, 1);
        }
        wg_commit();
        wg_wait<1>();
        if (lane == 0) mbar_arrive(bars + 8 * (kb == 4 ? B_E3 : B_EMPTY1 + ((kb - 1) & 3)));
      }
      mbar_wait(bars + 8 * B_EPOCH, 0);
      const uint32_t tag = lds32(sb + OFF_EPOCH) + 1;
      mbar_wait(bars + 8 * B_S3, 0);
      wg_wait<0>();
      pin<120>(acc);
      if (lane == 0) mbar_arrive(bars + 8 * B_P1);
      TSM(w == 0, 3 + wg);
      attention(acc, sb, b, wg, w, lane, tag);
    } else {
      const int tw = tid & 127, chl = 64 * (b & 1) + 8 * w + (lane >> 2);
      uint4* up = g_U + chl * U_PITCH + ((4 * (b >> 1) + (lane & 3)) ^ ((b >> 2) & 1));
      uint2 sw[10];
      uint32_t dv = 0;
      if (lane < 5) dv = __ldg(reinterpret_cast<const unsigned short*>(p.ssm_D) + 5 * b + lane);
#pragma unroll
      for (int i = 0; i < 10; i++) sw[i] = ldg64(reinterpret_cast<const uint2*>(p.shift_k) + chl + 128 * (i >> 1) + 32 * (i & 1));
      uint32_t tab[12];
      uint32_t tt[2];
      fft_tables(tab, tw);
      fft_twiddles(tt, tw);
      uint4 res[10];
#pragma unroll
      for (int i = 0; i < 10; i++) res[i] = make_uint4(0, 0, 0, 0);
#pragma unroll 1
      for (int slab = 0; slab < 5; slab++) {
#pragma unroll
        for (int i = 0; i < 8; i++) res[i] = res[i + 2];
        prep_slab(res + 8, sw, sb, slab, w, lane);
        TSIF(w == 0, 99 + 4 * slab);
#pragma unroll
        for (int i = 0; i < 8; i++) sw[i] = sw[i + 2];
      }
      TSIF(w == 0, 28);
      __syncwarp();
      if (lane == 0) mbar_arrive(bars + 8 * B_KVD + ((res[8].x ^ res[9].x) & p.zero));
      mbar_wait(bars + 8 * B_KVD, 0);
      fft_tables_store(tab, sb, tw);
      mbar_wait(bars + 8 * B_LAST, 0);
#pragma unroll
      for (int i = 0; i < 10; i++) up[(128 * (i >> 1) + 32 * (i & 1)) * U_PITCH] = res[i];
      __syncwarp();
      if (lane == 0) mbar_arrive(bars + 8 * B_PREP);
      TSIF(w == 0, 5);
      mbar_wait(bars + 8 * B_LAST, 0);
      prep_gate(p, sb, b, w, lane);
      __syncwarp();
      if (lane == 0) mbar_arrive(bars + 8 * B_GATE);
      TSIF(w == 0, 72);
      mbar_wait(bars + 8 * B_HB, 0);
      TSIF(w == 0, 2);
      const uint32_t ha = sb + U_BYTES + ((tw >> 3) * 16 + 8 + (tw & 7)) * 16;
      uint4 hv[5];
#pragma unroll
      for (int c = 0; c < 5; c++) hv[c] = lds128(ha + off_ch(c));
      __syncwarp();
#pragma unroll
      for (int c = 0; c < 5; c++) sts128((ha ^ 16) + off_ch(c), hv[c].x, hv[c].y, hv[c].z, hv[c].w);
      asm volatile("st.shared.v2.u32 [%0], {%1, %2};" ::"r"(sb + OFF_TT + 8 * tw), "r"(tt[0]), "r"(tt[1]) : "memory");
      if (tw < 5) asm volatile("st.shared.f32 [%0], %1;" ::"r"(sb + OFF_D + 4 * tw), "f"(bf_lo(dv) * 0.125f) : "memory");
      fence_async_smem();
      __syncwarp();
      if (lane == 0) mbar_arrive(bars + 8 * B_HA);
      TSIF(w == 0, 6);
    }

    FftConst fc;
    TSM(w == 0 && wg == 0, 104);
    mbar_wait(bars + 8 * B_HA, 0);
    fft_matrices(fc, sb, w, lane);
    TSM(w == 0 && wg == 0, 105);
    TSM(w == 0 && wg == 2, 124);
#pragma unroll 1
    for (uint32_t tasks = wg == 0 ? TASK0 : wg == 1 ? TASK1 : TASK2; tasks; tasks >>= 4) {
      const int c = (tasks & 7) - 1;
      conv_channel(fc, sb, c, wg, w, lane);
      if (lane == 0) mbar_arrive(bars + 8 * (B_YST + c));
      TSM(w == 0, 10 + c);
    }

    if (wg < 2) {
      const int g = lane >> 2;
      float acc[40];
#pragma unroll
      for (int i = 0; i < 40; i++) acc[i] = 0.f;
      const uint32_t da = desc_lo(sb + wg * 1024, 2048), db = desc_lo(sb, 2560);
      mbar_wait(bars + 8 * B_ORB, 0);
      mbar_wait(bars + 8 * B_FULL2, 0);
      mbar_wait(bars + 8 * B_CVD, 0);
      TSM(w == 0, 15 + wg);
#pragma unroll 1
      for (int j = 0; j < 8; j++) {
        mbar_wait(bars + 8 * (B_FULL2 + j), 0);
        TSM(w == 0 && wg == 0, 44 + (j < 4 ? j : j + 6));
        const uint32_t oa = da + (off_o(j) >> 4), ob = db + (off_w(j) >> 4);
        wg_fence();
#pragma unroll
        for (int k = 0; k < 5; k++) WgSST<80>::mma<HI_NONE, HI_SW32>(acc, oa + 256 * k, ob + 32 * k, 1);
        wg_commit();
        wg_wait<1>();
        if (j >= 1 && j <= 4 && lane == 0) mbar_arrive(bars + 8 * (B_EMPTY2 + j - 1));
      }
      TSIF(w == 0 && wg == 0, 113);
      const int tr = 64 * wg + 16 * w + (lane & 15);
      const uint32_t fm = sb + OFF_QS + tr * 128, fx = (lane >> 4) ^ (tr & 7);
      const uint32_t ft = sb + OFF_QT + tr * 32 + (((lane >> 4) ^ (tr >> 2)) & 1) * 16;
      const float g0 = __uint_as_float(lds32(sb + OFF_GATE + (64 * wg + 16 * w + g) * 4));
      const float g1 = __uint_as_float(lds32(sb + OFF_GATE + (64 * wg + 16 * w + 8 + g) * 4));
      const uint32_t ga = pack2(g0, g0), gb = pack2(g1, g1);
      const uint32_t na = pack2(1.f - g0, 1.f - g0), nb = pack2(1.f - g1, 1.f - g1);

      uint32_t qf[20];
      mbar_wait(bars + 8 * B_QF, 0);
      TSM(w == 0 && wg == 0, 99);
#pragma unroll
      for (int j = 0; j < 5; j++) ldsm4(qf + 4 * j, j < 4 ? fm + ((fx ^ (2 * j)) << 4) : ft);
#pragma unroll
      for (int i = 0; i < 20; i++) {
        qf[i] = bmul((i & 1) ? gb : ga, qf[i]);
        asm volatile("" : "+r"(qf[i]));
      }

      wg_wait<0>();
      pin<40>(acc);
      TSM(w == 0, 17 + wg);
      uint32_t pb[20];
#pragma unroll
      for (int j = 0; j < 10; j++) {
        pb[2 * j] = bmul(na, pack2(acc[4 * j], acc[4 * j + 1]));
        pb[2 * j + 1] = bmul(nb, pack2(acc[4 * j + 2], acc[4 * j + 3]));
        asm volatile("" : "+r"(pb[2 * j]), "+r"(pb[2 * j + 1]));
      }
      const uint32_t ya = sb + OFF_YT + wg * 10240 + ((lane >> 4) * 8 + (lane & 7)) * 128 +
                          (((2 * w + (((lane >> 3) & 1) ^ wg)) ^ (lane & 7)) << 4);
      mbar_wait(bars + 8 * B_YFULL, 0);
      TSM(w == 0 && wg == 0, 19);
#pragma unroll
      for (int j = 0; j < 5; j++) {
        uint32_t y[4];
        ldsm4t(y, ya + 2048 * j);
#pragma unroll
        for (int i = 0; i < 4; i++)
          qf[4 * j + i] = bfma(qf[4 * j + i], y[i], pb[4 * j + i]);
      }
#pragma unroll
      for (int j = 0; j < 5; j++) stsm4(j < 4 ? fm + ((fx ^ (2 * j)) << 4) : ft, qf + 4 * j);
      fence_async_smem();
      __syncwarp();
      if (lane == 0) {
        const int row = 64 * wg + 16 * w;
        asm volatile("cp.async.bulk.tensor.2d.global.shared::cta.bulk_group [%0, {%2, %3}], [%1];"
                     ::"l"(&m.om), "r"(sb + OFF_QS + row * 128), "r"(80 * hg), "r"(128 * r + row) : "memory");
        asm volatile("cp.async.bulk.tensor.2d.global.shared::cta.bulk_group [%0, {%2, %3}], [%1];"
                     ::"l"(&m.ot), "r"(sb + OFF_QT + row * 32), "r"(80 * hg + 64), "r"(128 * r + row) : "memory");
        asm volatile("cp.async.bulk.commit_group;\ncp.async.bulk.wait_group.read 0;" ::: "memory");
      }
      TSM(w == 0 || w == 3, 40 + 2 * wg + (w & 1));
    }
  }
}

typedef CUresult (*EncodeFn)(CUtensorMap*, CUtensorMapDataType, cuuint32_t, void*, const cuuint64_t*, const cuuint64_t*,
                             const cuuint32_t*, const cuuint32_t*, CUtensorMapInterleave, CUtensorMapSwizzle,
                             CUtensorMapL2promotion, CUtensorMapFloatOOBfill);

void encode(EncodeFn fn, CUtensorMap* tm, const void* base, int rank, const cuuint64_t* dims, const cuuint64_t* strides,
            const cuuint32_t* box, CUtensorMapSwizzle swz) {
  const cuuint32_t ones[3] = {1, 1, 1};
  fn(tm, CU_TENSOR_MAP_DATA_TYPE_BFLOAT16, rank, const_cast<void*>(base), dims, strides, box, ones,
     CU_TENSOR_MAP_INTERLEAVE_NONE, swz, CU_TENSOR_MAP_L2_PROMOTION_L2_128B, CU_TENSOR_MAP_FLOAT_OOB_FILL_NONE);
}

}

extern "C" void kernel_launch(void* const* d_in, const int* in_sizes, int n_in, void* d_out, int out_size) {
  (void)in_sizes; (void)n_in; (void)out_size;
  Params p;
  p.q = (const __nv_bfloat16*)d_in[0];
  p.k = (const __nv_bfloat16*)d_in[1];
  p.v = (const __nv_bfloat16*)d_in[2];
  p.shift_k = (const __nv_bfloat16*)d_in[3];
  p.ssm_k = (const __nv_bfloat16*)d_in[4];
  p.ssm_D = (const __nv_bfloat16*)d_in[5];
  p.wqkv = (const __nv_bfloat16*)d_in[7];
  p.wo = (const __nv_bfloat16*)d_in[8];
  p.gate_w = (const __nv_bfloat16*)d_in[9];
  p.out = (__nv_bfloat16*)d_out;
  p.zero = 0;

  static EncodeFn fn = nullptr;
  static void* yaddr = nullptr;
  if (!fn) {
    cudaDriverEntryPointQueryResult qr;
    void* f = nullptr;
    cudaGetDriverEntryPoint("cuTensorMapEncodeTiled", &f, cudaEnableDefault, &qr);
    fn = (EncodeFn)f;
    cudaGetSymbolAddress(&yaddr, g_U);
    cudaFuncSetAttribute(fused_kernel, cudaFuncAttributeMaxDynamicSharedMemorySize, SMEM_BYTES);
  }
  Maps m;
  {
    const cuuint64_t dims[3] = {640, 1024, 2}, st[2] = {2560, 1280};
    const cuuint32_t box[3] = {64, 64, 2};
    encode(fn, &m.x, p.q, 3, dims, st, box, CU_TENSOR_MAP_SWIZZLE_128B);
  }
  {
    const cuuint64_t dims[3] = {640, 640, 3}, st[2] = {3840, 1280};
    const cuuint32_t box[3] = {64, 64, 3}, boxt[3] = {16, 64, 3};
    encode(fn, &m.wm, p.wqkv, 3, dims, st, box, CU_TENSOR_MAP_SWIZZLE_128B);
    encode(fn, &m.wt, p.wqkv, 3, dims, st, boxt, CU_TENSOR_MAP_SWIZZLE_32B);
  }
  {
    const cuuint64_t dims[3] = {64, 2048, 10}, st[2] = {1280, 128};
    const cuuint32_t boxk[3] = {64, 35, 1}, boxv[3] = {64, 32, 1};
    encode(fn, &m.k, p.k, 3, dims, st, boxk, CU_TENSOR_MAP_SWIZZLE_128B);
    encode(fn, &m.v, p.v, 3, dims, st, boxv, CU_TENSOR_MAP_SWIZZLE_128B);
  }
  {
    const cuuint64_t dims[3] = {16, 640, 40}, st[2] = {1280, 32};
    const cuuint32_t box[3] = {16, 40, 5};
    encode(fn, &m.wo, p.wo, 3, dims, st, box, CU_TENSOR_MAP_SWIZZLE_32B);
  }
  {
    const cuuint64_t dims[2] = {2048, 640}, st[1] = {U_PITCH * 16};
    const cuuint32_t box[2] = {64, 80};
    encode(fn, &m.y, yaddr, 2, dims, st, box, CU_TENSOR_MAP_SWIZZLE_128B);
  }
  {
    const cuuint64_t dims[2] = {640, 2048}, st[1] = {1280};
    const cuuint32_t bqm[2] = {64, 128}, bqt[2] = {16, 128}, bom[2] = {64, 16}, bot[2] = {16, 16};
    encode(fn, &m.qm, p.q, 2, dims, st, bqm, CU_TENSOR_MAP_SWIZZLE_128B);
    encode(fn, &m.qt, p.q, 2, dims, st, bqt, CU_TENSOR_MAP_SWIZZLE_32B);
    encode(fn, &m.om, p.out, 2, dims, st, bom, CU_TENSOR_MAP_SWIZZLE_128B);
    encode(fn, &m.ot, p.out, 2, dims, st, bot, CU_TENSOR_MAP_SWIZZLE_32B);
  }
  fused_kernel<<<NCTA, NTHR, SMEM_BYTES>>>(m, p);
}
```

```cpp
#include <cuda.h>
#include <cuda_bf16.h>
#include <cuda_runtime.h>
#include <stdint.h>

namespace {

constexpr int SEQ = 2048, DIM = 640, NCTA = 128, NTHR = 512;

#define TRIG_KB 9
#define KV_KB 2
#define DEV_EXIT 0
#define FENCE_LO 0
#define FENCE_HI 0
#define WB_TRIG B_USIG
#define T_ISSUE 256
#define HR_AT 2
#define T_INIT 448
#define TASK0 0x3
#define TASK1 0x52
#define TASK2 0x41
#define WL_TRIG B_WOP

constexpr uint32_t STAGE_BYTES = 47104, ST_W = 16384, ST_WT = 40960;
constexpr uint32_t O_BYTES = 20480, WO_BYTES = 12800;
constexpr uint32_t OFF_OA = 0;
constexpr uint32_t OFF_QS = 3 * O_BYTES, OFF_QT = OFF_QS + 16384;
constexpr uint32_t OFF_WC = 81920;
constexpr uint32_t OFF_WA = 94720;
constexpr uint32_t OFF_GATE = 145920;
constexpr uint32_t OFF_TT = 146432;
constexpr uint32_t OFF_KVX = 148480;
constexpr uint32_t OFF_CH3 = 163840;
constexpr uint32_t CH_BYTES = 12288, U_BYTES = 4096;
constexpr uint32_t OFF_FT = 225280, OFF_GT = 229376;
constexpr uint32_t OFF_CH0 = 188416;
constexpr uint32_t OFF_KVS = OFF_CH0, KVS_V = 4480, KVS_BYTES = 8576;
constexpr uint32_t OFF_YT = 163840;
constexpr uint32_t OFF_BAR = 231936;
constexpr uint32_t SMEM_BYTES = OFF_BAR + 512;

enum : uint32_t {
  B_EMPTY1 = 0, B_S3 = 3, B_E3 = 4, B_EMPTY2 = 5, B_ATTN = 9, B_P1 = 10,
  B_GATE = 11, B_HA = 12, B_KVD = 13, B_PREP = 14, B_YST = 15,
  B_CVD = 20,
  B_FULL2 = 21, B_U = 29, B_KV = 33, B_HB = 38, B_C34 = 39, B_YRB = 40, B_YFULL = 41, B_EPOCH = 42, B_LAST = 43, B_OSIG = 44,
  B_WOP = 45, B_USIG = 46, B_WST = 47, B_QF = 48, B_ORB = 49, B_YSIG = 50,
  B_F0 = 51, B_FULL1 = 52
};
constexpr uint32_t OFF_EPOCH = OFF_BAR + 8 * 58, OFF_D = OFF_BAR + 8 * 60;
__device__ __forceinline__ uint32_t off_o(int j) { return j < 4 ? OFF_OA + j * O_BYTES : j < 6 ? OFF_CH0 + (j - 4) * O_BYTES : OFF_OA + (j - 6) * O_BYTES; }
__device__ __forceinline__ uint32_t off_w(int j) { return j < 4 ? OFF_WA + j * WO_BYTES : j == 4 ? OFF_KVX : j == 5 ? OFF_WC : OFF_WA + (j - 6) * WO_BYTES; }
__device__ __forceinline__ int step_src(int hg, int j) { return j == 0 ? hg : j <= hg ? j - 1 : j; }
__device__ __forceinline__ bool tail_first(int hg) { return (hg & 3) == 3; }
__device__ __forceinline__ uint32_t off_ch(int c) { return (c < 3 ? OFF_CH0 : OFF_CH3 - 3 * CH_BYTES) + c * CH_BYTES; }

#define U_PITCH 264
__device__ __align__(1024) uint4 g_U[DIM * U_PITCH];
__device__ uint4 g_O[NCTA * 1280];
__device__ uint4 g_WO[64 * 800];
__device__ uint4 g_halo[NCTA * 2 * 7 * 32];
__device__ __align__(128) float g_gate[SEQ];
__device__ unsigned g_cnt[32 * (1 + 2 * 16 + 8 + NCTA)];
constexpr int C_LAUNCH = 0, C_PREP = 32, C_Y = 32 * 17, C_W = 32 * 33, C_O = 32 * 41;

#define TSM(cond, slot) do { } while (0)
#define TSIF(cond, slot) do { if (__LINE__ >= FENCE_LO && __LINE__ < FENCE_HI) sched_fence(); } while (0)
__device__ __forceinline__ void sched_fence() {
  asm volatile("{\n.reg .pred p;\n.reg .u32 c;\nmov.u32 c, %%clock;\nsetp.eq.u32 p, c, 0;\n@p st.shared.u32 [%0], c;\n}"
               ::"r"(1024 + OFF_EPOCH + 4) : "memory");
}
#define TS(slot) TSIF(true, slot)

struct Params {
  const __nv_bfloat16 *q, *k, *v, *shift_k, *ssm_k, *ssm_D, *wqkv, *wo, *gate_w;
  __nv_bfloat16* out;
  uint32_t zero;
};

constexpr int SPIN_LIMIT = 1 << 17;

__device__ __forceinline__ void mbar_init(uint32_t bar, uint32_t count) {
  asm volatile("mbarrier.init.shared::cta.b64 [%0], %1;" ::"r"(bar), "r"(count) : "memory");
}
__device__ __forceinline__ void mbar_expect_tx(uint32_t bar, uint32_t bytes) {
  asm volatile("mbarrier.arrive.expect_tx.shared::cta.b64 _, [%0], %1;" ::"r"(bar), "r"(bytes) : "memory");
}
__device__ __forceinline__ void mbar_arrive(uint32_t bar) {
  asm volatile("mbarrier.arrive.shared::cta.b64 _, [%0];" ::"r"(bar) : "memory");
}
__device__ __forceinline__ void mbar_wait(uint32_t bar, uint32_t parity) {
  uint32_t ok;
  int spins = 0;
  do {
      asm volatile("{\n.reg .pred p;\nmbarrier.try_wait.parity.shared::cta.b64 p, [%1], %2;\nselp.b32 %0, 1, 0, p;\n}"
                   : "=r"(ok) : "r"(bar), "r"(parity) : "memory");
    if (++spins > SPIN_LIMIT) break;
  } while (!ok);
}
__device__ __forceinline__ unsigned flag_read(const unsigned* p) {
  unsigned v;
  asm volatile("ld.relaxed.gpu.global.u32 %0, [%1];" : "=r"(v) : "l"(p) : "memory");
  return v;
}
__device__ __forceinline__ void flag_poll(const unsigned* p, unsigned target) {
  unsigned v;
  int spins = 0;
  do {
    asm volatile("ld.relaxed.gpu.global.u32 %0, [%1];" : "=r"(v) : "l"(p) : "memory");
    if (++spins > SPIN_LIMIT) break;
  } while ((int)(v - target) < 0);
}
__device__ __forceinline__ void flag_wait(const unsigned* p, unsigned target) {
  flag_poll(p, target);
}
__device__ __forceinline__ void flag_signal(unsigned* p, int n, int lane) {
  if (lane == 0) asm volatile("fence.release.gpu;" ::: "memory");
  __syncwarp();
  if (lane < n) asm volatile("red.relaxed.gpu.global.add.u32 [%0], 1;" ::"l"(p + 32 * lane) : "memory");
}
__device__ __forceinline__ void flag_bump(unsigned* p) {
  asm volatile("red.relaxed.gpu.global.add.u32 [%0], 1;" ::"l"(p) : "memory");
}
__device__ __forceinline__ void fence_async_smem() { asm volatile("fence.proxy.async.shared::cta;" ::: "memory"); }
__device__ __forceinline__ void wg_sync(int id) { asm volatile("bar.sync %0, 128;" ::"r"(id) : "memory"); }

__device__ __forceinline__ void tma_2d(uint32_t dst, const CUtensorMap* tm, int c0, int c1, uint32_t bar) {
  asm volatile("cp.async.bulk.tensor.2d.shared::cluster.global.mbarrier::complete_tx::bytes [%0], [%1, {%3, %4}], [%2];"
               ::"r"(dst), "l"(tm), "r"(bar), "r"(c0), "r"(c1) : "memory");
}
__device__ __forceinline__ void tma_3d(uint32_t dst, const CUtensorMap* tm, int c0, int c1, int c2, uint32_t bar) {
  asm volatile("cp.async.bulk.tensor.3d.shared::cluster.global.mbarrier::complete_tx::bytes [%0], [%1, {%3, %4, %5}], [%2];"
               ::"r"(dst), "l"(tm), "r"(bar), "r"(c0), "r"(c1), "r"(c2) : "memory");
}
__device__ __forceinline__ void bulk_load(uint32_t dst, const void* src, uint32_t bytes, uint32_t bar) {
  asm volatile("cp.async.bulk.shared::cluster.global.mbarrier::complete_tx::bytes [%0], [%1], %2, [%3];"
               ::"r"(dst), "l"(src), "r"(bytes), "r"(bar) : "memory");
}
__device__ __forceinline__ void bulk_store(void* dst, uint32_t src, uint32_t bytes) {
  asm volatile("cp.async.bulk.global.shared::cta.bulk_group [%0], [%1], %2;" ::"l"(dst), "r"(src), "r"(bytes) : "memory");
}
__device__ __forceinline__ void bulk_wait_read() {
  asm volatile("cp.async.bulk.commit_group;\ncp.async.bulk.wait_group.read 0;" ::: "memory");
}

__device__ __forceinline__ void publish(void* dst, uint32_t src, uint32_t bytes, uint32_t bar) {
  bulk_store(dst, src, bytes);
  bulk_wait_read();
  bulk_load(src, dst, bytes, bar);
}

__device__ __forceinline__ void wg_fence() { asm volatile("wgmma.fence.sync.aligned;" ::: "memory"); }
__device__ __forceinline__ void wg_commit() { asm volatile("wgmma.commit_group.sync.aligned;" ::: "memory"); }
template <int N> __device__ __forceinline__ void wg_wait() { asm volatile("wgmma.wait_group.sync.aligned %0;" ::"n"(N) : "memory"); }
__device__ __forceinline__ uint32_t desc_lo(uint32_t addr, uint32_t lbo) { return ((addr & 0x3FFFF) >> 4) | ((lbo >> 4) << 16); }
constexpr uint32_t desc_hi(uint32_t sbo, uint32_t swz) { return (sbo >> 4) | (swz << 30); }
constexpr uint32_t HI_SW128 = desc_hi(1024, 1), HI_SW64 = desc_hi(512, 2), HI_SW32 = desc_hi(256, 3), HI_NONE = desc_hi(128, 0);
template <int N> __device__ __forceinline__ void pin(float* d) {
#pragma unroll
  for (int i = 0; i < N; i++) asm volatile("" : "+f"(d[i])::"memory");
}

__device__ __forceinline__ uint32_t lds32(uint32_t a) {
  uint32_t v;
  asm volatile("ld.volatile.shared.u32 %0, [%1];" : "=r"(v) : "r"(a) : "memory");
  return v;
}
__device__ __forceinline__ uint2 ldg64(const void* a) {
  uint2 v;
  asm volatile("ld.global.nc.v2.u32 {%0, %1}, [%2];" : "=r"(v.x), "=r"(v.y) : "l"(a) : "memory");
  return v;
}
__device__ __forceinline__ void ldsm4(uint32_t* r, uint32_t a) {
  asm volatile("ldmatrix.sync.aligned.m8n8.x4.shared.b16 {%0, %1, %2, %3}, [%4];"
               : "=r"(r[0]), "=r"(r[1]), "=r"(r[2]), "=r"(r[3]) : "r"(a) : "memory");
}
__device__ __forceinline__ void ldsm4t(uint32_t* r, uint32_t a) {
  asm volatile("ldmatrix.sync.aligned.m8n8.x4.trans.shared.b16 {%0, %1, %2, %3}, [%4];"
               : "=r"(r[0]), "=r"(r[1]), "=r"(r[2]), "=r"(r[3]) : "r"(a) : "memory");
}
__device__ __forceinline__ uint2 lds64(uint32_t a) {
  uint2 v;
  asm volatile("ld.shared.v2.u32 {%0, %1}, [%2];" : "=r"(v.x), "=r"(v.y) : "r"(a) : "memory");
  return v;
}
__device__ __forceinline__ uint4 lds128(uint32_t a) {
  uint4 v;
  asm volatile("ld.shared.v4.u32 {%0, %1, %2, %3}, [%4];" : "=r"(v.x), "=r"(v.y), "=r"(v.z), "=r"(v.w) : "r"(a) : "memory");
  return v;
}
__device__ __forceinline__ void sts128(uint32_t a, uint32_t x, uint32_t y, uint32_t z, uint32_t w) {
  asm volatile("st.shared.v4.u32 [%0], {%1, %2, %3, %4};" ::"r"(a), "r"(x), "r"(y), "r"(z), "r"(w) : "memory");
}
__device__ __forceinline__ void stsm4(uint32_t a, const uint32_t* r) {
  asm volatile("stmatrix.sync.aligned.m8n8.x4.shared.b16 [%0], {%1, %2, %3, %4};" ::"r"(a), "r"(r[0]), "r"(r[1]), "r"(r[2]), "r"(r[3]) : "memory");
}
__device__ __forceinline__ uint32_t pack2(float lo, float hi) {
  uint32_t r;
  asm("cvt.rn.bf16x2.f32 %0, %1, %2;" : "=r"(r) : "f"(hi), "f"(lo));
  return r;
}
__device__ __forceinline__ uint32_t movm(uint32_t a) {
  uint32_t d;
  asm volatile("movmatrix.sync.aligned.m8n8.trans.b16 %0, %1;" : "=r"(d) : "r"(a));
  return d;
}
__device__ __forceinline__ uint32_t bmul(uint32_t a, uint32_t b) {
  uint32_t d;
  asm("mul.rn.bf16x2 %0, %1, %2;" : "=r"(d) : "r"(a), "r"(b));
  return d;
}
__device__ __forceinline__ uint32_t badd(uint32_t a, uint32_t b) {
  uint32_t d;
  asm("add.rn.bf16x2 %0, %1, %2;" : "=r"(d) : "r"(a), "r"(b));
  return d;
}
__device__ __forceinline__ uint32_t bfma(uint32_t a, uint32_t b, uint32_t c) {
  uint32_t d;
  asm("fma.rn.bf16x2 %0, %1, %2, %3;" : "=r"(d) : "r"(a), "r"(b), "r"(c));
  return d;
}
__device__ __forceinline__ float bf_lo(uint32_t x) { return __uint_as_float(x << 16); }
__device__ __forceinline__ float bf_hi(uint32_t x) { return __uint_as_float(x & 0xFFFF0000u); }
__device__ __forceinline__ float ex2(float x) {
  float y;
  asm("ex2.approx.ftz.f32 %0, %1;" : "=f"(y) : "f"(x));
  return y;
}
__device__ __forceinline__ float rcp(float x) {
  float y;
  asm("rcp.approx.ftz.f32 %0, %1;" : "=f"(y) : "f"(x));
  return y;
}
__device__ __forceinline__ void mma16816(float* d, uint32_t a0, uint32_t a1, uint32_t a2, uint32_t a3, uint32_t b0, uint32_t b1) {
  asm volatile("mma.sync.aligned.m16n8k16.row.col.f32.bf16.bf16.f32 {%0, %1, %2, %3}, {%4, %5, %6, %7}, {%8, %9}, {%0, %1, %2, %3};"
               : "+f"(d[0]), "+f"(d[1]), "+f"(d[2]), "+f"(d[3])
               : "r"(a0), "r"(a1), "r"(a2), "r"(a3), "r"(b0), "r"(b1));
}
__device__ __forceinline__ void mma1688(float* d, uint32_t a0, uint32_t a1, uint32_t b0) {
  asm volatile("mma.sync.aligned.m16n8k8.row.col.f32.bf16.bf16.f32 {%0, %1, %2, %3}, {%4, %5}, {%6}, {%0, %1, %2, %3};"
               : "+f"(d[0]), "+f"(d[1]), "+f"(d[2]), "+f"(d[3])
               : "r"(a0), "r"(a1), "r"(b0));
}

template <int N> struct WgRS;
template <int N> struct WgSST;
template <> struct WgRS<32> {
  template <uint32_t HB>
  static __device__ __forceinline__ void mma(float* d, const uint32_t* a, uint32_t db) {
    asm volatile("{\n.reg .pred p;\n.reg .b64 db;\nsetp.ne.b32 p, %22, 0;\n"
      "mov.b64 db, {%20, %21};\n"
      "wgmma.mma_async.sync.aligned.m64n32k16.f32.bf16.bf16 {"
      "%0, %1, %2, %3, %4, %5, %6, %7, %8, %9, %10, %11, %12, %13, %14, %15"
      "}, {%16, %17, %18, %19}, db, p, 1, 1, 1;\n}\n"
      : "+f"(d[0]), "+f"(d[1]), "+f"(d[2]), "+f"(d[3]), "+f"(d[4]), "+f"(d[5]), "+f"(d[6]), "+f"(d[7]),
        "+f"(d[8]), "+f"(d[9]), "+f"(d[10]), "+f"(d[11]), "+f"(d[12]), "+f"(d[13]), "+f"(d[14]), "+f"(d[15])
      : "r"(a[0]), "r"(a[1]), "r"(a[2]), "r"(a[3]), "r"(db), "n"(HB), "n"(1));
  }
  template <uint32_t HB>
  static __device__ __forceinline__ void set(float* d, const uint32_t* a, uint32_t db) {
    asm volatile("{\n.reg .pred p;\n.reg .b64 db;\nsetp.ne.b32 p, %22, 0;\n"
      "mov.b64 db, {%20, %21};\n"
      "wgmma.mma_async.sync.aligned.m64n32k16.f32.bf16.bf16 {"
      "%0, %1, %2, %3, %4, %5, %6, %7, %8, %9, %10, %11, %12, %13, %14, %15"
      "}, {%16, %17, %18, %19}, db, p, 1, 1, 1;\n}\n"
      : "=f"(d[0]), "=f"(d[1]), "=f"(d[2]), "=f"(d[3]), "=f"(d[4]), "=f"(d[5]), "=f"(d[6]), "=f"(d[7]),
        "=f"(d[8]), "=f"(d[9]), "=f"(d[10]), "=f"(d[11]), "=f"(d[12]), "=f"(d[13]), "=f"(d[14]), "=f"(d[15])
      : "r"(a[0]), "r"(a[1]), "r"(a[2]), "r"(a[3]), "r"(db), "n"(HB), "n"(0));
  }
};
template <> struct WgRS<64> {
  template <uint32_t HB>
  static __device__ __forceinline__ void mma(float* d, const uint32_t* a, uint32_t db) {
    asm volatile("{\n.reg .pred p;\n.reg .b64 db;\nsetp.ne.b32 p, %38, 0;\n"
      "mov.b64 db, {%36, %37};\n"
      "wgmma.mma_async.sync.aligned.m64n64k16.f32.bf16.bf16 {"
      "%0, %1, %2, %3, %4, %5, %6, %7, %8, %9, %10, %11, %12, %13, %14, %15, "
      "%16, %17, %18, %19, %20, %21, %22, %23, %24, %25, %26, %27, %28, %29, %30, %31"
      "}, {%32, %33, %34, %35}, db, p, 1, 1, 1;\n}\n"
      : "+f"(d[0]), "+f"(d[1]), "+f"(d[2]), "+f"(d[3]), "+f"(d[4]), "+f"(d[5]), "+f"(d[6]), "+f"(d[7]),
        "+f"(d[8]), "+f"(d[9]), "+f"(d[10]), "+f"(d[11]), "+f"(d[12]), "+f"(d[13]), "+f"(d[14]), "+f"(d[15]),
        "+f"(d[16]), "+f"(d[17]), "+f"(d[18]), "+f"(d[19]), "+f"(d[20]), "+f"(d[21]), "+f"(d[22]), "+f"(d[23]),
        "+f"(d[24]), "+f"(d[25]), "+f"(d[26]), "+f"(d[27]), "+f"(d[28]), "+f"(d[29]), "+f"(d[30]), "+f"(d[31])
      : "r"(a[0]), "r"(a[1]), "r"(a[2]), "r"(a[3]), "r"(db), "n"(HB), "n"(1));
  }
  template <uint32_t HB>
  static __device__ __forceinline__ void set(float* d, const uint32_t* a, uint32_t db) {
    asm volatile("{\n.reg .pred p;\n.reg .b64 db;\nsetp.ne.b32 p, %38, 0;\n"
      "mov.b64 db, {%36, %37};\n"
      "wgmma.mma_async.sync.aligned.m64n64k16.f32.bf16.bf16 {"
      "%0, %1, %2, %3, %4, %5, %6, %7, %8, %9, %10, %11, %12, %13, %14, %15, "
      "%16, %17, %18, %19, %20, %21, %22, %23, %24, %25, %26, %27, %28, %29, %30, %31"
      "}, {%32, %33, %34, %35}, db, p, 1, 1, 1;\n}\n"
      : "=f"(d[0]), "=f"(d[1]), "=f"(d[2]), "=f"(d[3]), "=f"(d[4]), "=f"(d[5]), "=f"(d[6]), "=f"(d[7]),
        "=f"(d[8]), "=f"(d[9]), "=f"(d[10]), "=f"(d[11]), "=f"(d[12]), "=f"(d[13]), "=f"(d[14]), "=f"(d[15]),
        "=f"(d[16]), "=f"(d[17]), "=f"(d[18]), "=f"(d[19]), "=f"(d[20]), "=f"(d[21]), "=f"(d[22]), "=f"(d[23]),
        "=f"(d[24]), "=f"(d[25]), "=f"(d[26]), "=f"(d[27]), "=f"(d[28]), "=f"(d[29]), "=f"(d[30]), "=f"(d[31])
      : "r"(a[0]), "r"(a[1]), "r"(a[2]), "r"(a[3]), "r"(db), "n"(HB), "n"(0));
  }
};
template <> struct WgSST<48> {
  template <uint32_t HA, uint32_t HB>
  static __device__ __forceinline__ void mma(float* d, uint32_t da, uint32_t db, int sc) {
    asm volatile("{\n.reg .pred p;\n.reg .b64 da, db;\nsetp.ne.b32 p, %28, 0;\n"
      "mov.b64 da, {%24, %25};\nmov.b64 db, {%26, %27};\n"
      "wgmma.mma_async.sync.aligned.m64n48k16.f32.bf16.bf16 {"
      "%0, %1, %2, %3, %4, %5, %6, %7, %8, %9, %10, %11, %12, %13, %14, %15, "
      "%16, %17, %18, %19, %20, %21, %22, %23"
      "}, da, db, p, 1, 1, 0, 1;\n}\n"
      : "+f"(d[0]), "+f"(d[1]), "+f"(d[2]), "+f"(d[3]), "+f"(d[4]), "+f"(d[5]), "+f"(d[6]), "+f"(d[7]),
        "+f"(d[8]), "+f"(d[9]), "+f"(d[10]), "+f"(d[11]), "+f"(d[12]), "+f"(d[13]), "+f"(d[14]), "+f"(d[15]),
        "+f"(d[16]), "+f"(d[17]), "+f"(d[18]), "+f"(d[19]), "+f"(d[20]), "+f"(d[21]), "+f"(d[22]), "+f"(d[23])
      : "r"(da), "n"(HA), "r"(db), "n"(HB), "r"(sc));
  }
};
template <> struct WgSST<80> {
  template <uint32_t HA, uint32_t HB>
  static __device__ __forceinline__ void mma(float* d, uint32_t da, uint32_t db, int sc) {
    asm volatile("{\n.reg .pred p;\n.reg .b64 da, db;\nsetp.ne.b32 p, %44, 0;\n"
      "mov.b64 da, {%40, %41};\nmov.b64 db, {%42, %43};\n"
      "wgmma.mma_async.sync.aligned.m64n80k16.f32.bf16.bf16 {"
      "%0, %1, %2, %3, %4, %5, %6, %7, %8, %9, %10, %11, %12, %13, %14, %15, "
      "%16, %17, %18, %19, %20, %21, %22, %23, %24, %25, %26, %27, %28, %29, %30, %31, "
      "%32, %33, %34, %35, %36, %37, %38, %39"
      "}, da, db, p, 1, 1, 0, 1;\n}\n"
      : "+f"(d[0]), "+f"(d[1]), "+f"(d[2]), "+f"(d[3]), "+f"(d[4]), "+f"(d[5]), "+f"(d[6]), "+f"(d[7]),
        "+f"(d[8]), "+f"(d[9]), "+f"(d[10]), "+f"(d[11]), "+f"(d[12]), "+f"(d[13]), "+f"(d[14]), "+f"(d[15]),
        "+f"(d[16]), "+f"(d[17]), "+f"(d[18]), "+f"(d[19]), "+f"(d[20]), "+f"(d[21]), "+f"(d[22]), "+f"(d[23]),
        "+f"(d[24]), "+f"(d[25]), "+f"(d[26]), "+f"(d[27]), "+f"(d[28]), "+f"(d[29]), "+f"(d[30]), "+f"(d[31]),
        "+f"(d[32]), "+f"(d[33]), "+f"(d[34]), "+f"(d[35]), "+f"(d[36]), "+f"(d[37]), "+f"(d[38]), "+f"(d[39])
      : "r"(da), "n"(HA), "r"(db), "n"(HB), "r"(sc));
  }
};
template <> struct WgSST<192> {
  template <uint32_t HA, uint32_t HB>
  static __device__ __forceinline__ void mma(float* d, uint32_t da, uint32_t db, int sc) {
    asm volatile("{\n.reg .pred p;\n.reg .b64 da, db;\nsetp.ne.b32 p, %100, 0;\n"
      "mov.b64 da, {%96, %97};\nmov.b64 db, {%98, %99};\n"
      "wgmma.mma_async.sync.aligned.m64n192k16.f32.bf16.bf16 {"
      "%0, %1, %2, %3, %4, %5, %6, %7, %8, %9, %10, %11, %12, %13, %14, %15, "
      "%16, %17, %18, %19, %20, %21, %22, %23, %24, %25, %26, %27, %28, %29, %30, %31, "
      "%32, %33, %34, %35, %36, %37, %38, %39, %40, %41, %42, %43, %44, %45, %46, %47, "
      "%48, %49, %50, %51, %52, %53, %54, %55, %56, %57, %58, %59, %60, %61, %62, %63, "
      "%64, %65, %66, %67, %68, %69, %70, %71, %72, %73, %74, %75, %76, %77, %78, %79, "
      "%80, %81, %82, %83, %84, %85, %86, %87, %88, %89, %90, %91, %92, %93, %94, %95"
      "}, da, db, p, 1, 1, 0, 1;\n}\n"
      : "+f"(d[0]), "+f"(d[1]), "+f"(d[2]), "+f"(d[3]), "+f"(d[4]), "+f"(d[5]), "+f"(d[6]), "+f"(d[7]),
        "+f"(d[8]), "+f"(d[9]), "+f"(d[10]), "+f"(d[11]), "+f"(d[12]), "+f"(d[13]), "+f"(d[14]), "+f"(d[15]),
        "+f"(d[16]), "+f"(d[17]), "+f"(d[18]), "+f"(d[19]), "+f"(d[20]), "+f"(d[21]), "+f"(d[22]), "+f"(d[23]),
        "+f"(d[24]), "+f"(d[25]), "+f"(d[26]), "+f"(d[27]), "+f"(d[28]), "+f"(d[29]), "+f"(d[30]), "+f"(d[31]),
        "+f"(d[32]), "+f"(d[33]), "+f"(d[34]), "+f"(d[35]), "+f"(d[36]), "+f"(d[37]), "+f"(d[38]), "+f"(d[39]),
        "+f"(d[40]), "+f"(d[41]), "+f"(d[42]), "+f"(d[43]), "+f"(d[44]), "+f"(d[45]), "+f"(d[46]), "+f"(d[47]),
        "+f"(d[48]), "+f"(d[49]), "+f"(d[50]), "+f"(d[51]), "+f"(d[52]), "+f"(d[53]), "+f"(d[54]), "+f"(d[55]),
        "+f"(d[56]), "+f"(d[57]), "+f"(d[58]), "+f"(d[59]), "+f"(d[60]), "+f"(d[61]), "+f"(d[62]), "+f"(d[63]),
        "+f"(d[64]), "+f"(d[65]), "+f"(d[66]), "+f"(d[67]), "+f"(d[68]), "+f"(d[69]), "+f"(d[70]), "+f"(d[71]),
        "+f"(d[72]), "+f"(d[73]), "+f"(d[74]), "+f"(d[75]), "+f"(d[76]), "+f"(d[77]), "+f"(d[78]), "+f"(d[79]),
        "+f"(d[80]), "+f"(d[81]), "+f"(d[82]), "+f"(d[83]), "+f"(d[84]), "+f"(d[85]), "+f"(d[86]), "+f"(d[87]),
        "+f"(d[88]), "+f"(d[89]), "+f"(d[90]), "+f"(d[91]), "+f"(d[92]), "+f"(d[93]), "+f"(d[94]), "+f"(d[95])
      : "r"(da), "n"(HA), "r"(db), "n"(HB), "r"(sc));
  }
};

struct FftConst {
  uint32_t f[2][4], fi[4][4];
  uint32_t ta[2][2], tb[2][2];
};
__device__ __forceinline__ void cis(int m, float scale, float& c, float& s) {
  const float a = (float)m * (-6.283185307179586f * scale);
  c = __cosf(a);
  s = __sinf(a);
}
__device__ __forceinline__ void fft_tables(uint32_t (&v)[12], int tw) {
  const int row = tw >> 2, ch = tw & 3;
#pragma unroll
  for (int i = 0; i < 4; i++) {
    float c[2], s[2], x[2];
#pragma unroll
    for (int e = 0; e < 2; e++) {
      cis((((32 * (8 * ch + 2 * i + e) + 15) * (4 * row - 63) + 2048) & 4095) - 2048, 1.f / 4096, c[e], s[e]);
      float gc, gs;
      cis((((row & 15) * (8 * (ch & 1) + 2 * i + e) + 8) & 15) - 8, 1.f / 16, gc, gs);
      x[e] = (row >> 4) == (ch >> 1) ? gc : (ch >> 1) ? gs : -gs;
    }
    v[i] = pack2(c[0] * 0.125f, c[1] * 0.125f);
    v[4 + i] = pack2(s[0] * 0.125f, s[1] * 0.125f);
    v[8 + i] = pack2(x[0], x[1]);
  }
#pragma unroll
  for (int i = 0; i < 12; i++) asm volatile("" : "+r"(v[i]));
}
__device__ __forceinline__ void fft_tables_store(const uint32_t (&v)[12], uint32_t sb, int tw) {
  const int row = tw >> 2;
  const uint32_t x = ((tw ^ (row >> 1)) & 3) << 4, a = sb + OFF_FT + (16 * (row >> 3) + (row & 7)) * 64 + x;
  sts128(a, v[0], v[1], v[2], v[3]);
  sts128(a + 512, v[4], v[5], v[6], v[7]);
  sts128(sb + OFF_GT + row * 64 + x, v[8], v[9], v[10], v[11]);
}
__device__ __forceinline__ void fft_twiddles(uint32_t (&v)[2], int tw) {
  float a[2], s[2];
#pragma unroll
  for (int i = 0; i < 2; i++) {
    float c;
    cis((2 * (2 * (tw & 3) + i) - 15) * (4 * (tw >> 2) - 63), 1.f / 4096, c, s[i]);
    a[i] = __fdividef(-s[i], 1.f + c);
  }
  v[0] = pack2(a[0], a[1]);
  v[1] = pack2(s[0], s[1]);
  asm volatile("" : "+r"(v[0]), "+r"(v[1]));
}
__device__ __forceinline__ void fft_matrices(FftConst& k, uint32_t sb, int w, int lane) {
  const uint32_t x = (lane >> 1) & 3;
  const uint2 t0 = lds64(sb + OFF_TT + 256 * w + 8 * lane), t1 = lds64(sb + OFF_TT + 256 * w + 8 * (lane ^ 3));
  k.ta[0][0] = t0.x;
  k.tb[0][0] = t0.y;
  k.ta[1][1] = __byte_perm(t1.x, 0, 0x1032);
  k.tb[1][1] = __byte_perm(t1.y, 0, 0x1032);
#pragma unroll
  for (int j = 0; j < 2; j++) {
    k.ta[1 - j][j] = k.ta[j][j] ^ 0x80008000u;
    k.tb[1 - j][j] = k.tb[j][j] ^ 0x80008000u;
    asm volatile("" : "+r"(k.ta[0][j]), "+r"(k.tb[0][j]), "+r"(k.ta[1][j]), "+r"(k.tb[1][j]));
  }
#pragma unroll
  for (int i = 0; i < 2; i++) {
    ldsm4(k.f[i], sb + OFF_FT + (16 * w + (lane & 15)) * 64 + (((2 * i + (lane >> 4)) ^ x) << 4));
    ldsm4t(k.fi[i], sb + OFF_FT + (32 * i + lane) * 64 + ((w ^ x) << 4));
#pragma unroll
    for (int j = 0; j < 4; j++) {
      k.fi[2 + i][j] = (j & 1) ? k.fi[i][j - 1] ^ 0x80008000u : k.fi[i][j + 1];
      asm volatile("" : "+r"(k.fi[2 + i][j]));
    }
  }
}
__device__ __forceinline__ void rot(uint32_t& x, uint32_t& y, uint32_t a, uint32_t b) {
  x = bfma(a, y, x);
  y = bfma(b, x, y);
  x = bfma(a, y, x);
}
__device__ __forceinline__ void twiddle_fwd(uint32_t (&a)[4][4], float* d, const FftConst& k) {
#pragma unroll
  for (int q = 0; q < 4; q++)
#pragma unroll
    for (int j = 0; j < 2; j++) {
      const float* x = d + 8 * q + 4 * j;
      uint32_t re = pack2(x[0], x[1]), im = pack2(x[2], x[3]);
      rot(re, im, k.ta[0][j], k.tb[0][j]);
      a[q & 2][2 * j + (q & 1)] = re;
      a[(q & 2) + 1][2 * j + (q & 1)] = im;
    }
}
__device__ __forceinline__ void g_step(float* d, const uint32_t (&a)[4][4], uint32_t dre, uint32_t dim) {
  WgRS<32>::set<HI_SW64>(d, a[0], dre);
  WgRS<32>::set<HI_SW64>(d + 16, a[2], dre);
  WgRS<32>::mma<HI_SW64>(d, a[1], dim);
  WgRS<32>::mma<HI_SW64>(d + 16, a[3], dim);
  wg_commit();
}

__device__ __forceinline__ void products(uint32_t (&a)[4][4], const float* H, const float* U, int p) {
#pragma unroll
  for (int j = 0; j < 2; j++)
#pragma unroll
    for (int m = 2 * p; m < 2 * p + 2; m++) {
      float pr[2], pi[2];
#pragma unroll
      for (int x = 0; x < 2; x++)
#pragma unroll
        for (int q = 0; q <= m; q++) {
          const int ih = 16 * (q >> 1) + 2 * (q & 1) + 4 * j + x, iu = 16 * ((m - q) >> 1) + 2 * ((m - q) & 1) + 4 * j + x;
          pr[x] = q ? fmaf(H[ih], U[iu], pr[x]) : H[ih] * U[iu];
          pi[x] = q ? fmaf(H[ih], U[iu + 8], pi[x]) : H[ih] * U[iu + 8];
          pr[x] = fmaf(-H[ih + 8], U[iu + 8], pr[x]);
          pi[x] = fmaf(H[ih + 8], U[iu], pi[x]);
        }
      a[m & 2][2 * j + (m & 1)] = pack2(pr[0], pr[1]);
      a[(m & 2) + 1][2 * j + (m & 1)] = pack2(pi[0], pi[1]);
    }
}

__device__ __forceinline__ void conv_channel(const FftConst& k, uint32_t sb, int c, int wg, int w, int lane) {
  const uint32_t cb = sb + off_ch(c), bars = sb + OFF_BAR;
  const uint32_t du = desc_lo(cb, 1024), dg = desc_lo(sb + OFF_GT, 16), dz = desc_lo(cb + U_BYTES, 16);
  float U[32], H[32];
  uint32_t a[4][4], e[4][4];
  const float dv = __uint_as_float(lds32(sb + OFF_D + 4 * c));
  wg_fence();
  WgRS<64>::set<HI_SW32>(H, k.f[0], du + 256);
  WgRS<64>::mma<HI_SW32>(H, k.f[1], du + 256 + 32);
  wg_commit();
  wg_wait<0>();
  pin<32>(H);
  twiddle_fwd(a, H, k);
  mbar_wait(bars + 8 * (B_U + (c < 3 ? c : 3)), 0);
  TSM(w == 0 && c < 3, 7 + wg);
  wg_fence();
  WgRS<64>::set<HI_SW32>(U, k.f[0], du);
  WgRS<64>::mma<HI_SW32>(U, k.f[1], du + 32);
  wg_commit();
  g_step(H, a, dg, dg + 64);
  wg_wait<1>();
  pin<32>(U);
  twiddle_fwd(e, U, k);
  wg_fence();
  g_step(U, e, dg, dg + 64);
  wg_wait<0>();
  pin<32>(U);
  pin<32>(H);
#pragma unroll
  for (int j = 0; j < 4; j++) H[4 * (j >> 1) + (j & 1)] += dv;
  float V[32];
#pragma unroll
  for (int p = 0; p < 2; p++) {
    products(a, H, U, p);
    wg_fence();
    WgRS<32>::set<HI_SW64>(V + 16 * p, a[2 * p], dg + 64);
    WgRS<32>::mma<HI_SW64>(V + 16 * p, a[2 * p + 1], dg);
    wg_commit();
  }
  const uint32_t za = cb + U_BYTES + (8 * w + (lane & 7)) * 128 + (((lane >> 3) ^ (lane & 7)) << 4);
  const uint32_t ya = cb + (lane >> 4) * 1024 + (8 * w + (lane & 7)) * 32 + ((((lane >> 3) ^ (lane >> 2)) & 1) << 4);
  wg_sync(1 + wg);
#pragma unroll
  for (int p = 0; p < 2; p++) {
    if (p == 0) wg_wait<1>();
    else wg_wait<0>();
    pin<16>(V + 16 * p);
#pragma unroll
    for (int i = 0; i < 4; i++) {
      const int j = i & 1;
      const float* x = V + 16 * p + 4 * j + (i & 2);
      e[p][i] = pack2(x[8], x[9]);
      e[2 + p][i] = pack2(x[0], x[1]);
      rot(e[p][i], e[2 + p][i], k.ta[1][j], k.tb[1][j]);
    }
    stsm4(za ^ (64 * p), e[p]);
    stsm4((za ^ (64 * p)) + 4096, e[2 + p]);
  }
  fence_async_smem();
  wg_sync(1 + wg);
  wg_fence();
  WgRS<64>::set<HI_SW128>(H, k.fi[0], dz);
#pragma unroll
  for (int ks = 1; ks < 4; ks++) WgRS<64>::mma<HI_SW128>(H, k.fi[ks], dz + 128 * ks);
  wg_commit();
  wg_wait<0>();
  pin<32>(H);
  if (lane == 0) mbar_arrive(bars + 8 * B_CVD);
  TSIF(w == 0, 88 + c);
#pragma unroll
  for (int j = 0; j < 8; j++)
    a[j >> 2][j & 3] = j < 2 ? pack2(H[4 * j], H[4 * j + 1]) : pack2(H[4 * j] + H[4 * j - 6], H[4 * j + 1] + H[4 * j - 5]);
  stsm4(ya, a[0]);
  stsm4(ya + 2048, a[1]);
  fence_async_smem();
  __syncwarp();
}

__device__ __forceinline__ void prep_slab(uint4* res, const uint2* sw, uint32_t sb, int slab, int w, int lane) {
  const int t = lane & 3, tp = (lane & 7) >> 1, pos = 8 * tp + 2 * (((lane >> 3) + tp) & 3) + (lane & 1);
  const uint32_t base = sb + OFF_KVS + slab * KVS_BYTES + pos * 128;
  uint32_t kk[2][4][4], vv[2][4];
  mbar_wait(sb + OFF_BAR + 8 * (B_KV + slab), 0);
#pragma unroll
  for (int h = 0; h < 2; h++) {
#pragma unroll
    for (int j = 0; j < 4; j++) {
      const uint32_t a = base + 128 * j;
      ldsm4t(kk[h][j], a + (((w + 4 * h) ^ ((a >> 7) & 7)) << 4));
    }
    const uint32_t a = base + KVS_V;
    ldsm4t(vv[h], a + (((w + 4 * h) ^ ((a >> 7) & 7)) << 4));
  }
#pragma unroll
  for (int h = 0; h < 2; h++) {
    uint32_t (&k)[4][4] = kk[h];
    uint32_t (&v)[4] = vv[h];
    const uint32_t w0 = __byte_perm(sw[h].x, 0, 0x1010), w1 = __byte_perm(sw[h].x, 0, 0x3232);
    const uint32_t w2 = __byte_perm(sw[h].y, 0, 0x1010), w3 = __byte_perm(sw[h].y, 0, 0x3232);
#pragma unroll
    for (int m = 0; m < 4; m++)
      v[m] = bmul(badd(badd(badd(bmul(k[0][m], w3), bmul(k[1][m], w2)), bmul(k[2][m], w1)), bmul(k[3][m], w0)), v[m]);
    uint32_t a[4];
#pragma unroll
    for (int m = 0; m < 4; m++) a[m] = (t & 1) ? v[(m + 3) & 3] : v[m];
    res[h] = (t & 2) ? make_uint4(a[2], a[3], a[0], a[1]) : make_uint4(a[0], a[1], a[2], a[3]);
  }
}

__device__ __forceinline__ void prep_gate(const Params& p, uint32_t sb, int b, int w, int lane) {
  uint2 gw[5], x[4][5];
#pragma unroll
  for (int j = 0; j < 5; j++) gw[j] = ldg64(reinterpret_cast<const uint2*>(p.gate_w) + lane + 32 * j);
#pragma unroll
  for (int i = 0; i < 4; i++)
#pragma unroll
    for (int j = 0; j < 5; j++)
      x[i][j] = ldg64(reinterpret_cast<const uint2*>(p.q) + (16 * b + 4 * w + i) * (DIM / 4) + lane + 32 * j);
  float s[4];
#pragma unroll
  for (int i = 0; i < 4; i++) {
    s[i] = 0.f;
#pragma unroll
    for (int j = 0; j < 5; j++) {
      const uint32_t m0 = bmul(x[i][j].x, gw[j].x), m1 = bmul(x[i][j].y, gw[j].y);
      s[i] += (bf_lo(m0) + bf_hi(m0)) + (bf_lo(m1) + bf_hi(m1));
    }
  }
  const bool h = lane & 16, q = lane & 8;
  const float a = (h ? s[2] : s[0]) + __shfl_xor_sync(0xffffffffu, h ? s[0] : s[2], 16);
  const float c = (h ? s[3] : s[1]) + __shfl_xor_sync(0xffffffffu, h ? s[1] : s[3], 16);
  float z = (q ? c : a) + __shfl_xor_sync(0xffffffffu, q ? a : c, 8);
#pragma unroll
  for (int o = 4; o > 0; o >>= 1) z += __shfl_xor_sync(0xffffffffu, z, o);
  z = bf_lo(pack2(z, 0.f));
  z = bf_lo(pack2(__fdividef(1.f, 1.f + __expf(-z)), 0.f));
  mbar_wait(sb + OFF_BAR + 8 * B_S3, 0);
  if ((lane & 7) == 0) asm volatile("st.shared.f32 [%0], %1;" ::"r"(sb + OFF_GATE + 64 * (b & 7) + 16 * w + (lane >> 1)), "f"(z) : "memory");
  fence_async_smem();
}

__device__ __forceinline__ uint32_t bmax(uint32_t a, uint32_t b) {
  uint32_t d;
  asm("max.bf16x2 %0, %1, %2;" : "=r"(d) : "r"(a), "r"(b));
  return d;
}
__device__ __forceinline__ void softmax_two(const float (&l)[2][2], uint32_t& p0, uint32_t& p1) {
  constexpr float kScale = 0.22360679774997896f, kLog2e = 1.4426950408889634f;
  const uint32_t r0 = pack2(l[0][0], l[1][0]), r1 = pack2(l[0][1], l[1][1]);
  const uint32_t x0 = pack2(bf_lo(r0) * kScale, bf_hi(r0) * kScale), x1 = pack2(bf_lo(r1) * kScale, bf_hi(r1) * kScale);
  uint32_t m = bmax(x0, x1);
  m = bmax(m, __shfl_xor_sync(0xffffffffu, m, 1));
  m = bmax(m, __shfl_xor_sync(0xffffffffu, m, 2));
  const float m0 = bf_lo(m) * kLog2e, m1 = bf_hi(m) * kLog2e;
  p0 = pack2(ex2(bf_lo(x0) * kLog2e - m0), ex2(bf_lo(x1) * kLog2e - m0));
  p1 = pack2(ex2(bf_hi(x0) * kLog2e - m1), ex2(bf_hi(x1) * kLog2e - m1));
}

__device__ __forceinline__ void halo_read(uint32_t (&kpv)[10], uint32_t (&vpv)[10], uint32_t (&tg)[7], const uint4* hp) {
#pragma unroll
  for (int j = 0; j < 7; j++) {
    uint32_t x0, x1, x2;
    asm volatile("ld.relaxed.gpu.global.v4.u32 {%0, %1, %2, %3}, [%4];"
                 : "=r"(x0), "=r"(x1), "=r"(x2), "=r"(tg[j]) : "l"(hp + 32 * j) : "memory");
    if (j < 4) kpv[3 * j] = x0; else vpv[3 * j - 10] = x0;
    if (j < 3) kpv[3 * j + 1] = x1; else vpv[3 * j - 9] = x1;
    if (j < 3) kpv[3 * j + 2] = x2; else if (j < 6) vpv[3 * j - 8] = x2;
  }
}

template <int ROT>
__device__ __forceinline__ void pack_qkv(const float* acc, uint32_t (&qlo)[10], uint32_t (&qhi)[10], uint32_t (&klo)[10],
                                         uint32_t (&khi)[10], uint32_t (&vlo)[10], uint32_t (&vhi)[10]) {
#pragma unroll
  for (int j = 0; j < 10; j++) {
    const int x = (j + ROT) % 10, tq = x < 8 ? x : 16 + x, tk = x < 8 ? 8 + x : 18 + x, tv = x < 8 ? 16 + x : 20 + x;
    khi[j] = pack2(acc[4 * tk + 2], acc[4 * tk + 3]);
    vhi[j] = movm(pack2(acc[4 * tv + 2], acc[4 * tv + 3]));
    qlo[j] = pack2(acc[4 * tq], acc[4 * tq + 1]);
    qhi[j] = pack2(acc[4 * tq + 2], acc[4 * tq + 3]);
    klo[j] = pack2(acc[4 * tk], acc[4 * tk + 1]);
    vlo[j] = pack2(acc[4 * tv], acc[4 * tv + 1]);
    asm volatile("" : "+r"(khi[j]), "+r"(qlo[j]), "+r"(qhi[j]), "+r"(klo[j]), "+r"(vlo[j]));
  }
}

template <int ROT> __device__ __forceinline__ void halo_send(const float* acc, uint4* ho, uint32_t tag) {
#pragma unroll
  for (int j = 0; j < 7; j++) {
    uint32_t x[3];
#pragma unroll
    for (int e = 0; e < 3; e++) {
      const int i = 3 * j + e, y = (i % 10 + ROT) % 10, tk = y < 8 ? 8 + y : 18 + y, tv = y < 8 ? 16 + y : 20 + y;
      x[e] = i < 10 ? pack2(acc[4 * tk + 2], acc[4 * tk + 3]) : i < 20 ? movm(pack2(acc[4 * tv + 2], acc[4 * tv + 3])) : 0u;
    }
    asm volatile("st.relaxed.gpu.global.v4.u32 [%0], {%1, %2, %3, %4};" ::"l"(ho + 32 * j), "r"(x[0]), "r"(x[1]), "r"(x[2]), "r"(tag) : "memory");
  }
}

__device__ __forceinline__ void attention(float* acc, uint32_t sb, int b, int par, int w, int lane, uint32_t tag) {
  const int g = lane >> 2, t = lane & 3;
  uint32_t klo[10], khi[10], vlo[10], vhi[10], qlo[10], qhi[10], kpv[10], vpv[10];
  if (w == 3 && b < NCTA - 8) {
    uint4* ho = g_halo + (b * 2 + par) * 224 + lane;
    if (tail_first(b & 7)) halo_send<8>(acc, ho, tag);
    else halo_send<0>(acc, ho, tag);
    TSIF(par == 0, 76);
    pin<120>(acc);
  }
  if (tail_first(b & 7)) pack_qkv<8>(acc, qlo, qhi, klo, khi, vlo, vhi);
  else pack_qkv<0>(acc, qlo, qhi, klo, khi, vlo, vhi);
  const uint32_t xa = sb + OFF_KVX + (par * 3) * 2560 + lane * 16;
  if (w < 3) {
    sts128(xa + w * 2560, khi[0], khi[1], khi[2], khi[3]);
    sts128(xa + w * 2560 + 512, khi[4], khi[5], khi[6], khi[7]);
    sts128(xa + w * 2560 + 1024, khi[8], khi[9], vhi[0], vhi[1]);
    sts128(xa + w * 2560 + 1536, vhi[2], vhi[3], vhi[4], vhi[5]);
    sts128(xa + w * 2560 + 2048, vhi[6], vhi[7], vhi[8], vhi[9]);
  }
  TSIF(par == 0 && w == 1, 64);
#pragma unroll
  for (int j = 0; j < 10; j++) vlo[j] = movm(vlo[j]);
  const bool far0 = 2 * t > g, far1 = 2 * t + 1 > g;
  const uint32_t mfar = (far0 ? 0x0000FFFFu : 0u) | (far1 ? 0xFFFF0000u : 0u);
  float slo[4][2], lg[2][2];
  uint32_t phi[4], plo[4], qml[4], qmh[4];
  const bool nohist = (w == 0) && (b < 8);
  const uint4* hp = g_halo + ((b - 8) * 2 + par) * 224 + lane;
  uint32_t tg[7];
#pragma unroll
  for (int h = 0; h < 4; h++) {
    if (h == HR_AT && w == 0 && !nohist) halo_read(kpv, vpv, tg, hp);
    const int f = h == 0 ? 0 : h == 1 ? 3 : h == 2 ? 5 : 8, hf = h < 2 ? 2 : 7;
    const bool mine = (h & 1) ? t >= 2 : t < 2;
    qml[h] = mine ? qlo[hf] : 0u;
    qmh[h] = mine ? qhi[hf] : 0u;
    float a[4] = {0.f, 0.f, 0.f, 0.f}, c[4] = {0.f, 0.f, 0.f, 0.f};
    mma16816(a, qlo[f], qhi[f], qlo[f + 1], qhi[f + 1], klo[f], klo[f + 1]);
    mma16816(c, qlo[f], qhi[f], qlo[f + 1], qhi[f + 1], khi[f], khi[f + 1]);
    mma1688(a, qml[h], qmh[h], klo[hf]);
    mma1688(c, qml[h], qmh[h], khi[hf]);
    slo[h][0] = a[0];
    slo[h][1] = a[1];
    lg[h & 1][0] = far0 ? a[2] : c[2];
    lg[h & 1][1] = far1 ? a[3] : c[3];
    if (h & 1) softmax_two(lg, phi[h - 1], phi[h]);
  }
  if (HR_AT == 4 && w == 0 && !nohist) halo_read(kpv, vpv, tg, hp);
  TSIF(par == 0 && w == 1, 65);
  wg_sync(1 + par);
  TSIF(par == 0 && w == 1, 66);
  if (w > 0) {
    const uint4 v0 = lds128(xa + (w - 1) * 2560), v1 = lds128(xa + (w - 1) * 2560 + 512), v2 = lds128(xa + (w - 1) * 2560 + 1024);
    const uint4 v3 = lds128(xa + (w - 1) * 2560 + 1536), v4 = lds128(xa + (w - 1) * 2560 + 2048);
    kpv[0] = v0.x; kpv[1] = v0.y; kpv[2] = v0.z; kpv[3] = v0.w; kpv[4] = v1.x; kpv[5] = v1.y; kpv[6] = v1.z; kpv[7] = v1.w;
    kpv[8] = v2.x; kpv[9] = v2.y; vpv[0] = v2.z; vpv[1] = v2.w; vpv[2] = v3.x; vpv[3] = v3.y; vpv[4] = v3.z; vpv[5] = v3.w;
    vpv[6] = v4.x; vpv[7] = v4.y; vpv[8] = v4.z; vpv[9] = v4.w;
  } else if (nohist) {
#pragma unroll
    for (int j = 0; j < 10; j++) kpv[j] = vpv[j] = 0u;
  } else if (HR_AT == 5) {
    TSIF(par == 0, 77);
    halo_read(kpv, vpv, tg, hp);
  }
  if (w == 0 && !nohist) {
    int spins = 0;
    while (true) {
      bool ok = true;
#pragma unroll
      for (int j = 0; j < 7; j++) ok = ok && tg[j] == tag;
      if (__all_sync(0xffffffffu, ok) || ++spins > SPIN_LIMIT) break;
      halo_read(kpv, vpv, tg, hp);
    }
    TSIF(par == 0, 79);
  }
#pragma unroll
  for (int h = 0; h < 4; h++) {
    const int f = h == 0 ? 0 : h == 1 ? 3 : h == 2 ? 5 : 8, hf = h < 2 ? 2 : 7;
    float a[4] = {0.f, 0.f, 0.f, 0.f};
    mma16816(a, qlo[f], qhi[f], qlo[f + 1], qhi[f + 1], kpv[f], kpv[f + 1]);
    mma1688(a, qml[h], qmh[h], kpv[hf]);
    const float ninf = __int_as_float(0xff800000);
    lg[h & 1][0] = far0 ? (nohist ? ninf : a[0]) : slo[h][0];
    lg[h & 1][1] = far1 ? (nohist ? ninf : a[1]) : slo[h][1];
    if (h & 1) softmax_two(lg, plo[h - 1], plo[h]);
  }
  TSIF(par == 0 && w <= 1, 67 + w);
  uint32_t ov[20];
#pragma unroll
  for (int hp = 0; hp < 2; hp++) {
    const int hf = hp ? 7 : 2;
    float sh[4] = {0.f, 0.f, 0.f, 0.f}, i0 = 0.f, i1 = 0.f;
#pragma unroll
    for (int e = 0; e < 2; e++) {
      const int h = 2 * hp + e, f = h == 0 ? 0 : h == 1 ? 3 : h == 2 ? 5 : 8;
      const uint32_t a0 = plo[h] & mfar, a2 = plo[h] & ~mfar, a3 = phi[h] & mfar, c1 = phi[h] & ~mfar;
      float sum[4] = {0.f, 0.f, 0.f, 0.f};
      mma1688(sum, plo[h], phi[h], 0x3F803F80u);
      const float r0 = rcp(sum[0]), r1 = rcp(sum[2]);
#pragma unroll
      for (int j = f; j < f + 2; j++) {
        float o[4] = {0.f, 0.f, 0.f, 0.f};
        mma16816(o, a0, 0u, a2, a3, vpv[j], vlo[j]);
        mma1688(o, 0u, c1, vhi[j]);
        ov[2 * j] = pack2(o[0] * r0, o[1] * r0);
        ov[2 * j + 1] = pack2(o[2] * r1, o[3] * r1);
      }
      const bool mine = e ? g >= 4 : g < 4;
      mma16816(sh, a0, 0u, a2, a3, mine ? vpv[hf] : 0u, mine ? vlo[hf] : 0u);
      mma1688(sh, 0u, c1, mine ? vhi[hf] : 0u);
      if (e == 0 || t >= 2) {
        i0 = r0;
        i1 = r1;
      }
    }
    ov[2 * hf] = pack2(sh[0] * i0, sh[1] * i0);
    ov[2 * hf + 1] = pack2(sh[2] * i1, sh[3] * i1);
  }
  TS(32 + 4 * par + w);
  mbar_wait(sb + OFF_BAR + 8 * B_P1, 0);
  const uint32_t oa = sb + OFF_OA + (lane >> 4) * 2048 + (32 * w + 2 * (lane & 15) + par) * 16;
#pragma unroll
  for (int j = 0; j < 5; j++) stsm4(oa + 4096 * j, ov + 4 * j);
  TSIF(par == 0 && w == 0, 120);
  fence_async_smem();
  TSIF(par == 0 && w == 0, 121);
  __syncwarp();
  if (lane == 0) mbar_arrive(sb + OFF_BAR + 8 * B_ATTN);
  TSM(w == 0 || w == 2, 122 + par + (w == 2 ? 3 : 0));
}

struct Maps {
  CUtensorMap x, wm, wt, k, v, y, wo, qm, qt, om, ot;
};

__device__ __forceinline__ void load_stage(uint32_t sb, int kb, int b, const Maps& m) {
  const uint32_t st = sb + (kb & 3) * STAGE_BYTES, bar = sb + OFF_BAR + 8 * (B_FULL1 + (kb & 3));
  const int r = b >> 3, hg = b & 7, slab = kb - KV_KB;
  const bool kv = slab >= 0 && slab < 5;
  const uint32_t kbar = sb + OFF_BAR + 8 * (B_KV + slab), dst = sb + OFF_KVS + slab * KVS_BYTES;
  mbar_expect_tx(bar, STAGE_BYTES);
  if (kv) mbar_expect_tx(kbar, KVS_BYTES);
  tma_3d(st, &m.x, 64 * kb, 64 * r, 0, bar);
  tma_3d(st + ST_W, &m.wm, 80 * hg + (tail_first(hg) ? 16 : 0), 64 * kb, 0, bar);
  tma_3d(st + ST_WT, &m.wt, 80 * hg + (tail_first(hg) ? 0 : 64), 64 * kb, 0, bar);
  if (kv) tma_3d(dst, &m.k, 0, 32 * (b >> 1) - 3, 2 * slab + (b & 1), kbar);
  if (kv) tma_3d(dst + KVS_V, &m.v, 0, 32 * (b >> 1), 2 * slab + (b & 1), kbar);
}

__global__ void __launch_bounds__(NTHR, 1) fused_kernel(const __grid_constant__ Maps m, const Params p) {
  extern __shared__ __align__(1024) uint8_t smem[];
  const uint32_t sb = (uint32_t)__cvta_generic_to_shared(smem);
  const uint32_t bars = sb + OFF_BAR;
  const int tid = threadIdx.x, lane = tid & 31;
  int b = blockIdx.x;
  b = (((b & 63) >> 3) * 2 + (b & 1)) * 8 + (((b < 64 ? 0x6521 : 0x7430) >> (4 * ((b >> 1) & 3))) & 7);
  const int r = b >> 3, hg = b & 7;

  if (tid == T_ISSUE) {
    TSM(true, 0);
    mbar_init(bars + 8 * B_F0, 1);
    fence_async_smem();
    mbar_expect_tx(bars + 8 * B_F0, ST_WT);
    tma_3d(sb, &m.x, 0, 64 * r, 0, bars + 8 * B_F0);
    tma_3d(sb + ST_W, &m.wm, 80 * hg + (tail_first(hg) ? 16 : 0), 0, 0, bars + 8 * B_F0);
#pragma unroll
    for (int i = 0; i < 4; i++) mbar_init(bars + 8 * (B_FULL1 + i), 1);
    fence_async_smem();
    mbar_expect_tx(bars + 8 * B_FULL1, STAGE_BYTES - ST_WT);
    tma_3d(sb + ST_WT, &m.wt, 80 * hg + (tail_first(hg) ? 0 : 64), 0, 0, bars + 8 * B_FULL1);
    load_stage(sb, 1, b, m);
  } else if (tid == T_INIT) {
#pragma unroll
    for (int i = 0; i < B_F0; i++) mbar_init(bars + 8 * i, i < B_GATE ? 8 : i < B_CVD ? 4 : i == B_CVD ? 20 : 1);
    fence_async_smem();
  }
  const int warp = __shfl_sync(0xffffffffu, tid >> 5, 0), wg = warp >> 2, w = warp & 3;
  __syncthreads();

  if (wg == 3) {
    asm volatile("setmaxnreg.dec.sync.aligned.u32 56;");
    if (w == 0) {
      if (lane == 0) {
#pragma unroll 1
        for (int kb = 2; kb < 10; kb++) {
          if (kb >= 4) mbar_wait(bars + 8 * (kb == 7 ? B_E3 : B_EMPTY1 + (kb & 3)), (kb >> 3) & 1);
          TSIF(kb >= 4, 44 + kb);
          load_stage(sb, kb, b, m);
          TSIF(kb == 3, 60);
          if (kb == TRIG_KB) mbar_arrive(bars + 8 * B_LAST);
        }
        mbar_wait(bars + 8 * B_WOP, 0);
        mbar_wait(bars + 8 * WL_TRIG, 0);
        mbar_wait(bars + 8 * B_EPOCH, 0);
        flag_wait(g_cnt + C_W + 32 * hg, (lds32(sb + OFF_EPOCH) + 1) * 16);
        TS(30);
#pragma unroll 1
        for (int j = 0; j < 8; j++) {
          if (j >= 6) mbar_wait(bars + 8 * (B_EMPTY2 + j - 6), 0);
          if (j == 4) mbar_wait(bars + 8 * B_ATTN, 0);
          TSIF(j >= 6, 100 + j);
          mbar_expect_tx(bars + 8 * (B_FULL2 + j), j == 0 ? WO_BYTES : j == 5 ? O_BYTES + WO_BYTES + 512 : O_BYTES + WO_BYTES);
          bulk_load(sb + off_w(j), g_WO + (hg * 8 + step_src(hg, j)) * 800, WO_BYTES, bars + 8 * (B_FULL2 + j));
        }
        mbar_wait(bars + 8 * (B_EMPTY2 + 3), 0);
        mbar_expect_tx(bars + 8 * B_QF, O_BYTES);
        tma_2d(sb + OFF_QS, &m.qm, 80 * hg, 128 * r, bars + 8 * B_QF);
        tma_2d(sb + OFF_QT, &m.qt, 80 * hg + 64, 128 * r, bars + 8 * B_QF);
      }
    } else if (w == 1) {
      unsigned epoch = 0;
      if (lane == 0) {
        epoch = atomicAdd(g_cnt + C_LAUNCH, 1u) / NCTA;
        asm volatile("st.shared.u32 [%0], %1;" ::"r"(sb + OFF_EPOCH), "r"(epoch) : "memory");
        mbar_arrive(bars + 8 * B_EPOCH);
        mbar_wait(bars + 8 * B_KVD, 0);
        mbar_expect_tx(bars + 8 * B_HB, 5 * 4096);
#pragma unroll 1
        for (int c = 0; c < 5; c++) {
          if (c == 3) mbar_wait(bars + 8 * B_S3, 0);
          bulk_load(sb + off_ch(c) + U_BYTES, p.ssm_k + (5 * b + c) * SEQ, 4096, bars + 8 * B_HB);
        }
#pragma unroll
        for (int c = 0; c < 4; c++) mbar_expect_tx(bars + 8 * (B_U + c), c < 3 ? U_BYTES : 2 * U_BYTES);
        const uint4* usrc = g_U + 5 * b * U_PITCH;
        mbar_wait(bars + 8 * B_USIG, 0);
        flag_wait(g_cnt + C_PREP + 32 * (b & 15), (epoch + 1) * NCTA);
        TS(23);
#pragma unroll
        for (int c = 0; c < 5; c++) {
          if (c == 3) mbar_wait(bars + 8 * (B_U + 2), 0);
          bulk_load(sb + off_ch(c), usrc + c * U_PITCH, U_BYTES, bars + 8 * (B_U + (c < 3 ? c : 3)));
          TSIF(c == 0 || c == 4, 116 + (c >> 2));
        }
      }
      epoch = __shfl_sync(0xffffffffu, epoch, 0);
      if (lane < 8) {
        const int src = (b & ~7) | step_src(hg, lane);
        mbar_wait(bars + 8 * B_ATTN, 0);
        TS(20);
        bool seen = false;
#pragma unroll 1
        for (int spins = 0; spins < SPIN_LIMIT; spins++) {
          const bool now = !seen && (int)(flag_read(g_cnt + C_O + 32 * src) - (epoch + 1)) >= 0;
          if (now && lane >= 1 && lane < 4) bulk_load(sb + off_o(lane), g_O + src * 1280, O_BYTES, bars + 8 * (B_FULL2 + lane));
          seen = seen || now;
          if (__all_sync(0xff, seen)) break;
        }
        TS(21);
        if (lane == 5) bulk_load(sb + OFF_GATE, g_gate + 128 * r, 512, bars + 8 * (B_FULL2 + 5));
#pragma unroll 1
        for (int j = 4; j < 8; j++) {
          if (lane == j) {
            mbar_wait(bars + 8 * (j < 6 ? B_C34 : B_EMPTY2 + j - 6), 0);
            bulk_load(sb + off_o(j), g_O + src * 1280, O_BYTES, bars + 8 * (B_FULL2 + j));
          }
          __syncwarp(0xff);
        }
        TS(22);
      }
    } else if (w == 2) {
      mbar_wait(bars + 8 * B_PREP, 0);
      flag_signal(g_cnt + C_PREP, 16, lane);
      TS(25);
      if (lane == 0) {
        mbar_arrive(bars + 8 * B_USIG);
        mbar_expect_tx(bars + 8 * B_ORB, O_BYTES + 64);
        mbar_wait(bars + 8 * B_GATE, 0);
        publish(g_gate + 16 * b, sb + OFF_GATE + 64 * hg, 64, bars + 8 * B_ORB);
        mbar_wait(bars + 8 * B_ATTN, 0);
        publish(g_O + b * 1280, sb + OFF_OA, O_BYTES, bars + 8 * B_ORB);
        TS(74);
        mbar_wait(bars + 8 * B_ORB, 0);
        flag_bump(g_cnt + C_O + 32 * b);
        TS(26);
        mbar_arrive(bars + 8 * B_OSIG);
      }
    } else {
      if (lane == 0) {
        uint4* dst = g_WO + (hg * 8 + (r >> 1)) * 800 + (r & 1) * 80;
        mbar_wait(bars + 8 * B_S3, 0);
        asm volatile("cp.async.bulk.prefetch.L2.global [%0], 6400;" ::"l"(p.wo + b * 3200) : "memory");
        mbar_wait(bars + 8 * B_P1, 0);
        mbar_wait(bars + 8 * WB_TRIG, 0);
        mbar_expect_tx(bars + 8 * B_WST, WO_BYTES / 2);
        tma_3d(sb + OFF_WA, &m.wo, 0, 40 * r, 5 * hg, bars + 8 * B_WST);
        mbar_wait(bars + 8 * B_WST, 0);
#pragma unroll 1
        for (int n = 0; n < 5; n++) bulk_store(dst + 160 * n, sb + OFF_WA + 1280 * n, 1280);
        bulk_wait_read();
        mbar_expect_tx(bars + 8 * B_WST, WO_BYTES / 2);
#pragma unroll 1
        for (int n = 0; n < 5; n++) bulk_load(sb + OFF_WA + 1280 * n, dst + 160 * n, 1280, bars + 8 * B_WST);
        mbar_wait(bars + 8 * B_WST, 1);
        flag_bump(g_cnt + C_W + 32 * hg);
        mbar_arrive(bars + 8 * B_WOP);
        TS(71);
        mbar_expect_tx(bars + 8 * B_C34, 3 * U_BYTES);
        mbar_expect_tx(bars + 8 * B_YRB, 2 * U_BYTES);
#pragma unroll 1
        for (int c = 0; c < 5; c++) {
          mbar_wait(bars + 8 * (B_YST + c), 0);
          publish(g_U + (5 * b + c) * U_PITCH, sb + off_ch(c), U_BYTES, bars + 8 * (c < 3 ? B_C34 : B_YRB));
        }
        TS(75);
        mbar_wait(bars + 8 * B_C34, 0);
        mbar_wait(bars + 8 * B_YRB, 0);
        flag_bump(g_cnt + C_Y + 32 * (b >> 4));
        TS(27);
        mbar_arrive(bars + 8 * B_YSIG);
        mbar_expect_tx(bars + 8 * B_YFULL, 20480);
        flag_wait(g_cnt + C_Y + 32 * hg, (lds32(sb + OFF_EPOCH) + 1) * 16);
        TS(24);
        tma_2d(sb + OFF_YT, &m.y, 128 * r, 80 * hg, bars + 8 * B_YFULL);
        tma_2d(sb + OFF_YT + 10240, &m.y, 128 * r + 64, 80 * hg, bars + 8 * B_YFULL);
      }
    }
  } else {
    asm volatile("setmaxnreg.inc.sync.aligned.u32 152;");
    if (wg < 2) {
      float acc[120];
#pragma unroll
      for (int i = 0; i < 120; i++) acc[i] = 0.f;
      const uint32_t da = desc_lo(sb + wg * 8192, 16), db = desc_lo(sb + ST_W, 8192), dc = desc_lo(sb + ST_WT, 2048);
      mbar_wait(bars + 8 * B_F0, 0);
      TSIF(w == 0 && wg == 0, 1);
      wg_fence();
#pragma unroll
      for (int k = 0; k < 4; k++) WgSST<192>::mma<HI_SW128, HI_SW128>(acc, da + 2 * k, db + 128 * k, 1);
      wg_commit();
      mbar_wait(bars + 8 * B_FULL1, 0);
      wg_fence();
#pragma unroll
      for (int k = 0; k < 4; k++) WgSST<48>::mma<HI_SW128, HI_SW32>(acc + 96, da + 2 * k, dc + 32 * k, 1);
      wg_commit();
#pragma unroll 1
      for (int kb = 1; kb < 10; kb++) {
        mbar_wait(bars + 8 * (B_FULL1 + (kb & 3)), (kb >> 2) & 1);
        const uint32_t so = (kb & 3) * (STAGE_BYTES >> 4);
        wg_fence();
#pragma unroll
        for (int k = 0; k < 4; k++) {
          WgSST<192>::mma<HI_SW128, HI_SW128>(acc, da + so + 2 * k, db + so + 128 * k, 1);
          WgSST<48>::mma<HI_SW128, HI_SW32>(acc + 96, da + so + 2 * k, dc + so + 32 * k, 1);
        }
        wg_commit();
        wg_wait<1>();
        if (lane == 0) mbar_arrive(bars + 8 * (kb == 4 ? B_E3 : B_EMPTY1 + ((kb - 1) & 3)));
      }
      mbar_wait(bars + 8 * B_EPOCH, 0);
      const uint32_t tag = lds32(sb + OFF_EPOCH) + 1;
      mbar_wait(bars + 8 * B_S3, 0);
      wg_wait<0>();
      pin<120>(acc);
      if (lane == 0) mbar_arrive(bars + 8 * B_P1);
      TSM(w == 0, 3 + wg);
      attention(acc, sb, b, wg, w, lane, tag);
    } else {
      const int tw = tid & 127, chl = 64 * (b & 1) + 8 * w + (lane >> 2);
      uint4* up = g_U + chl * U_PITCH + ((4 * (b >> 1) + (lane & 3)) ^ ((b >> 2) & 1));
      uint2 sw[10];
      uint32_t dv = 0;
      if (lane < 5) dv = __ldg(reinterpret_cast<const unsigned short*>(p.ssm_D) + 5 * b + lane);
#pragma unroll
      for (int i = 0; i < 10; i++) sw[i] = ldg64(reinterpret_cast<const uint2*>(p.shift_k) + chl + 128 * (i >> 1) + 32 * (i & 1));
      uint32_t tab[12];
      uint32_t tt[2];
      fft_tables(tab, tw);
      fft_twiddles(tt, tw);
      uint4 res[10];
#pragma unroll
      for (int i = 0; i < 10; i++) res[i] = make_uint4(0, 0, 0, 0);
#pragma unroll 1
      for (int slab = 0; slab < 5; slab++) {
#pragma unroll
        for (int i = 0; i < 8; i++) res[i] = res[i + 2];
        prep_slab(res + 8, sw, sb, slab, w, lane);
        TSIF(w == 0, 99 + 4 * slab);
#pragma unroll
        for (int i = 0; i < 8; i++) sw[i] = sw[i + 2];
      }
      TSIF(w == 0, 28);
      __syncwarp();
      if (lane == 0) mbar_arrive(bars + 8 * B_KVD + ((res[8].x ^ res[9].x) & p.zero));
      mbar_wait(bars + 8 * B_KVD, 0);
      fft_tables_store(tab, sb, tw);
      mbar_wait(bars + 8 * B_LAST, 0);
#pragma unroll
      for (int i = 0; i < 10; i++) up[(128 * (i >> 1) + 32 * (i & 1)) * U_PITCH] = res[i];
      __syncwarp();
      if (lane == 0) mbar_arrive(bars + 8 * B_PREP);
      TSIF(w == 0, 5);
      mbar_wait(bars + 8 * B_LAST, 0);
      prep_gate(p, sb, b, w, lane);
      __syncwarp();
      if (lane == 0) mbar_arrive(bars + 8 * B_GATE);
      TSIF(w == 0, 72);
      mbar_wait(bars + 8 * B_HB, 0);
      TSIF(w == 0, 2);
      const uint32_t ha = sb + U_BYTES + ((tw >> 3) * 16 + 8 + (tw & 7)) * 16;
      uint4 hv[5];
#pragma unroll
      for (int c = 0; c < 5; c++) hv[c] = lds128(ha + off_ch(c));
      __syncwarp();
#pragma unroll
      for (int c = 0; c < 5; c++) sts128((ha ^ 16) + off_ch(c), hv[c].x, hv[c].y, hv[c].z, hv[c].w);
      asm volatile("st.shared.v2.u32 [%0], {%1, %2};" ::"r"(sb + OFF_TT + 8 * tw), "r"(tt[0]), "r"(tt[1]) : "memory");
      if (tw < 5) asm volatile("st.shared.f32 [%0], %1;" ::"r"(sb + OFF_D + 4 * tw), "f"(bf_lo(dv) * 0.125f) : "memory");
      fence_async_smem();
      __syncwarp();
      if (lane == 0) mbar_arrive(bars + 8 * B_HA);
      TSIF(w == 0, 6);
    }

    FftConst fc;
    TSM(w == 0 && wg == 0, 104);
    mbar_wait(bars + 8 * B_HA, 0);
    fft_matrices(fc, sb, w, lane);
    TSM(w == 0 && wg == 0, 105);
    TSM(w == 0 && wg == 2, 124);
#pragma unroll 1
    for (uint32_t tasks = wg == 0 ? TASK0 : wg == 1 ? TASK1 : TASK2; tasks; tasks >>= 4) {
      const int c = (tasks & 7) - 1;
      conv_channel(fc, sb, c, wg, w, lane);
      if (lane == 0) mbar_arrive(bars + 8 * (B_YST + c));
      TSM(w == 0, 10 + c);
    }

    if (wg < 2) {
      const int g = lane >> 2;
      float acc[40];
#pragma unroll
      for (int i = 0; i < 40; i++) acc[i] = 0.f;
      const uint32_t da = desc_lo(sb + wg * 1024, 2048), db = desc_lo(sb, 2560);
      mbar_wait(bars + 8 * B_ORB, 0);
      mbar_wait(bars + 8 * B_FULL2, 0);
      mbar_wait(bars + 8 * B_CVD, 0);
      TSM(w == 0, 15 + wg);
#pragma unroll 1
      for (int j = 0; j < 8; j++) {
        mbar_wait(bars + 8 * (B_FULL2 + j), 0);
        TSM(w == 0 && wg == 0, 44 + (j < 4 ? j : j + 6));
        const uint32_t oa = da + (off_o(j) >> 4), ob = db + (off_w(j) >> 4);
        wg_fence();
#pragma unroll
        for (int k = 0; k < 5; k++) WgSST<80>::mma<HI_NONE, HI_SW32>(acc, oa + 256 * k, ob + 32 * k, 1);
        wg_commit();
        wg_wait<1>();
        if (j >= 1 && j <= 4 && lane == 0) mbar_arrive(bars + 8 * (B_EMPTY2 + j - 1));
      }
      TSIF(w == 0 && wg == 0, 113);
      const int tr = 64 * wg + 16 * w + (lane & 15);
      const uint32_t fm = sb + OFF_QS + tr * 128, fx = (lane >> 4) ^ (tr & 7);
      const uint32_t ft = sb + OFF_QT + tr * 32 + (((lane >> 4) ^ (tr >> 2)) & 1) * 16;
      const float g0 = __uint_as_float(lds32(sb + OFF_GATE + (64 * wg + 16 * w + g) * 4));
      const float g1 = __uint_as_float(lds32(sb + OFF_GATE + (64 * wg + 16 * w + 8 + g) * 4));
      const uint32_t ga = pack2(g0, g0), gb = pack2(g1, g1);
      const uint32_t na = pack2(1.f - g0, 1.f - g0), nb = pack2(1.f - g1, 1.f - g1);

      uint32_t qf[20];
      mbar_wait(bars + 8 * B_QF, 0);
      TSM(w == 0 && wg == 0, 99);
#pragma unroll
      for (int j = 0; j < 5; j++) ldsm4(qf + 4 * j, j < 4 ? fm + ((fx ^ (2 * j)) << 4) : ft);
#pragma unroll
      for (int i = 0; i < 20; i++) {
        qf[i] = bmul((i & 1) ? gb : ga, qf[i]);
        asm volatile("" : "+r"(qf[i]));
      }

      wg_wait<0>();
      pin<40>(acc);
      TSM(w == 0, 17 + wg);
      uint32_t pb[20];
#pragma unroll
      for (int j = 0; j < 10; j++) {
        pb[2 * j] = bmul(na, pack2(acc[4 * j], acc[4 * j + 1]));
        pb[2 * j + 1] = bmul(nb, pack2(acc[4 * j + 2], acc[4 * j + 3]));
        asm volatile("" : "+r"(pb[2 * j]), "+r"(pb[2 * j + 1]));
      }
      const uint32_t ya = sb + OFF_YT + wg * 10240 + ((lane >> 4) * 8 + (lane & 7)) * 128 +
                          (((2 * w + (((lane >> 3) & 1) ^ wg)) ^ (lane & 7)) << 4);
      mbar_wait(bars + 8 * B_YFULL, 0);
      TSM(w == 0 && wg == 0, 19);
#pragma unroll
      for (int j = 0; j < 5; j++) {
        uint32_t y[4];
        ldsm4t(y, ya + 2048 * j);
#pragma unroll
        for (int i = 0; i < 4; i++)
          qf[4 * j + i] = bfma(qf[4 * j + i], y[i], pb[4 * j + i]);
      }
#pragma unroll
      for (int j = 0; j < 5; j++) stsm4(j < 4 ? fm + ((fx ^ (2 * j)) << 4) : ft, qf + 4 * j);
      fence_async_smem();
      __syncwarp();
      if (lane == 0) {
        const int row = 64 * wg + 16 * w;
        asm volatile("cp.async.bulk.tensor.2d.global.shared::cta.bulk_group [%0, {%2, %3}], [%1];"
                     ::"l"(&m.om), "r"(sb + OFF_QS + row * 128), "r"(80 * hg), "r"(128 * r + row) : "memory");
        asm volatile("cp.async.bulk.tensor.2d.global.shared::cta.bulk_group [%0, {%2, %3}], [%1];"
                     ::"l"(&m.ot), "r"(sb + OFF_QT + row * 32), "r"(80 * hg + 64), "r"(128 * r + row) : "memory");
        asm volatile("cp.async.bulk.commit_group;\ncp.async.bulk.wait_group.read 0;" ::: "memory");
      }
      TSM(w == 0 || w == 3, 40 + 2 * wg + (w & 1));
    }
  }
}

typedef CUresult (*EncodeFn)(CUtensorMap*, CUtensorMapDataType, cuuint32_t, void*, const cuuint64_t*, const cuuint64_t*,
                             const cuuint32_t*, const cuuint32_t*, CUtensorMapInterleave, CUtensorMapSwizzle,
                             CUtensorMapL2promotion, CUtensorMapFloatOOBfill);

void encode(EncodeFn fn, CUtensorMap* tm, const void* base, int rank, const cuuint64_t* dims, const cuuint64_t* strides,
            const cuuint32_t* box, CUtensorMapSwizzle swz) {
  const cuuint32_t ones[3] = {1, 1, 1};
  fn(tm, CU_TENSOR_MAP_DATA_TYPE_BFLOAT16, rank, const_cast<void*>(base), dims, strides, box, ones,
     CU_TENSOR_MAP_INTERLEAVE_NONE, swz, CU_TENSOR_MAP_L2_PROMOTION_L2_128B, CU_TENSOR_MAP_FLOAT_OOB_FILL_NONE);
}

}

extern "C" void kernel_launch(void* const* d_in, const int* in_sizes, int n_in, void* d_out, int out_size) {
  (void)in_sizes; (void)n_in; (void)out_size;
  Params p;
  p.q = (const __nv_bfloat16*)d_in[0];
  p.k = (const __nv_bfloat16*)d_in[1];
  p.v = (const __nv_bfloat16*)d_in[2];
  p.shift_k = (const __nv_bfloat16*)d_in[3];
  p.ssm_k = (const __nv_bfloat16*)d_in[4];
  p.ssm_D = (const __nv_bfloat16*)d_in[5];
  p.wqkv = (const __nv_bfloat16*)d_in[7];
  p.wo = (const __nv_bfloat16*)d_in[8];
  p.gate_w = (const __nv_bfloat16*)d_in[9];
  p.out = (__nv_bfloat16*)d_out;
  p.zero = 0;

  static EncodeFn fn = nullptr;
  static void* yaddr = nullptr;
  if (!fn) {
    cudaDriverEntryPointQueryResult qr;
    void* f = nullptr;
    cudaGetDriverEntryPoint("cuTensorMapEncodeTiled", &f, cudaEnableDefault, &qr);
    fn = (EncodeFn)f;
    cudaGetSymbolAddress(&yaddr, g_U);
    cudaFuncSetAttribute(fused_kernel, cudaFuncAttributeMaxDynamicSharedMemorySize, SMEM_BYTES);
  }
  Maps m;
  {
    const cuuint64_t dims[3] = {640, 1024, 2}, st[2] = {2560, 1280};
    const cuuint32_t box[3] = {64, 64, 2};
    encode(fn, &m.x, p.q, 3, dims, st, box, CU_TENSOR_MAP_SWIZZLE_128B);
  }
  {
    const cuuint64_t dims[3] = {640, 640, 3}, st[2] = {3840, 1280};
    const cuuint32_t box[3] = {64, 64, 3}, boxt[3] = {16, 64, 3};
    encode(fn, &m.wm, p.wqkv, 3, dims, st, box, CU_TENSOR_MAP_SWIZZLE_128B);
    encode(fn, &m.wt, p.wqkv, 3, dims, st, boxt, CU_TENSOR_MAP_SWIZZLE_32B);
  }
  {
    const cuuint64_t dims[3] = {64, 2048, 10}, st[2] = {1280, 128};
    const cuuint32_t boxk[3] = {64, 35, 1}, boxv[3] = {64, 32, 1};
    encode(fn, &m.k, p.k, 3, dims, st, boxk, CU_TENSOR_MAP_SWIZZLE_128B);
    encode(fn, &m.v, p.v, 3, dims, st, boxv, CU_TENSOR_MAP_SWIZZLE_128B);
  }
  {
    const cuuint64_t dims[3] = {16, 640, 40}, st[2] = {1280, 32};
    const cuuint32_t box[3] = {16, 40, 5};
    encode(fn, &m.wo, p.wo, 3, dims, st, box, CU_TENSOR_MAP_SWIZZLE_32B);
  }
  {
    const cuuint64_t dims[2] = {2048, 640}, st[1] = {U_PITCH * 16};
    const cuuint32_t box[2] = {64, 80};
    encode(fn, &m.y, yaddr, 2, dims, st, box, CU_TENSOR_MAP_SWIZZLE_128B);
  }
  {
    const cuuint64_t dims[2] = {640, 2048}, st[1] = {1280};
    const cuuint32_t bqm[2] = {64, 128}, bqt[2] = {16, 128}, bom[2] = {64, 16}, bot[2] = {16, 16};
    encode(fn, &m.qm, p.q, 2, dims, st, bqm, CU_TENSOR_MAP_SWIZZLE_128B);
    encode(fn, &m.qt, p.q, 2, dims, st, bqt, CU_TENSOR_MAP_SWIZZLE_32B);
    encode(fn, &m.om, p.out, 2, dims, st, bom, CU_TENSOR_MAP_SWIZZLE_128B);
    encode(fn, &m.ot, p.out, 2, dims, st, bot, CU_TENSOR_MAP_SWIZZLE_32B);
  }
  fused_kernel<<<NCTA, NTHR, SMEM_BYTES>>>(m, p);
}
```

```cpp
#include <cuda.h>
#include <cuda_bf16.h>
#include <cuda_runtime.h>
#include <stdint.h>

namespace {

constexpr int SEQ = 2048, DIM = 640, NCTA = 128, NTHR = 512;

#define TRIG_KB 9
#define KV_KB 2
#define DEV_EXIT 0
#define FENCE_LO 0
#define FENCE_HI 0
#define WB_TRIG B_USIG
#define T_ISSUE 256
#define HR_AT 5
#define HALO_INIT 1
#define T_INIT 448
#define TASK0 0x3
#define TASK1 0x52
#define TASK2 0x41
#define WL_TRIG B_WOP

constexpr uint32_t STAGE_BYTES = 47104, ST_W = 16384, ST_WT = 40960;
constexpr uint32_t O_BYTES = 20480, WO_BYTES = 12800;
constexpr uint32_t OFF_OA = 0;
constexpr uint32_t OFF_QS = 3 * O_BYTES, OFF_QT = OFF_QS + 16384;
constexpr uint32_t OFF_WC = 81920;
constexpr uint32_t OFF_WA = 94720;
constexpr uint32_t OFF_GATE = 145920;
constexpr uint32_t OFF_TT = 146432;
constexpr uint32_t OFF_KVX = 148480;
constexpr uint32_t OFF_CH3 = 163840;
constexpr uint32_t CH_BYTES = 12288, U_BYTES = 4096;
constexpr uint32_t OFF_FT = 225280, OFF_GT = 229376;
constexpr uint32_t OFF_CH0 = 188416;
constexpr uint32_t OFF_KVS = OFF_CH0, KVS_V = 4480, KVS_BYTES = 8576;
constexpr uint32_t OFF_YT = 163840;
constexpr uint32_t OFF_BAR = 231936;
constexpr uint32_t SMEM_BYTES = OFF_BAR + 512;

enum : uint32_t {
  B_EMPTY1 = 0, B_S3 = 3, B_E3 = 4, B_EMPTY2 = 5, B_ATTN = 9, B_P1 = 10,
  B_GATE = 11, B_HA = 12, B_KVD = 13, B_PREP = 14, B_YST = 15,
  B_CVD = 20,
  B_FULL2 = 21, B_U = 29, B_KV = 33, B_HB = 38, B_C34 = 39, B_YRB = 40, B_YFULL = 41, B_EPOCH = 42, B_LAST = 43, B_OSIG = 44,
  B_WOP = 45, B_USIG = 46, B_WST = 47, B_QF = 48, B_ORB = 49, B_YSIG = 50,
  B_F0 = 51, B_FULL1 = 52
};
constexpr uint32_t OFF_EPOCH = OFF_BAR + 8 * 58, OFF_D = OFF_BAR + 8 * 60;
__device__ __forceinline__ uint32_t off_o(int j) { return j < 4 ? OFF_OA + j * O_BYTES : j < 6 ? OFF_CH0 + (j - 4) * O_BYTES : OFF_OA + (j - 6) * O_BYTES; }
__device__ __forceinline__ uint32_t off_w(int j) { return j < 4 ? OFF_WA + j * WO_BYTES : j == 4 ? OFF_KVX : j == 5 ? OFF_WC : OFF_WA + (j - 6) * WO_BYTES; }
__device__ __forceinline__ int step_src(int hg, int j) { return j == 0 ? hg : j <= hg ? j - 1 : j; }
__device__ __forceinline__ bool tail_first(int hg) { return (hg & 3) == 3; }
__device__ __forceinline__ uint32_t off_ch(int c) { return (c < 3 ? OFF_CH0 : OFF_CH3 - 3 * CH_BYTES) + c * CH_BYTES; }

#define U_PITCH 264
__device__ __align__(1024) uint4 g_U[DIM * U_PITCH];
__device__ uint4 g_O[NCTA * 1280];
__device__ uint4 g_WO[64 * 800];
__device__ uint4 g_halo[NCTA * 2 * 7 * 32];
__device__ __align__(128) float g_gate[SEQ];
__device__ unsigned g_cnt[32 * (1 + 2 * 16 + 8 + NCTA)];
constexpr int C_LAUNCH = 0, C_PREP = 32, C_Y = 32 * 17, C_W = 32 * 33, C_O = 32 * 41;

#define TSM(cond, slot) do { } while (0)
#define TSIF(cond, slot) do { if (__LINE__ >= FENCE_LO && __LINE__ < FENCE_HI) sched_fence(); } while (0)
__device__ __forceinline__ void sched_fence() {
  asm volatile("{\n.reg .pred p;\n.reg .u32 c;\nmov.u32 c, %%clock;\nsetp.eq.u32 p, c, 0;\n@p st.shared.u32 [%0], c;\n}"
               ::"r"(1024 + OFF_EPOCH + 4) : "memory");
}
#define TS(slot) TSIF(true, slot)

struct Params {
  const __nv_bfloat16 *q, *k, *v, *shift_k, *ssm_k, *ssm_D, *wqkv, *wo, *gate_w;
  __nv_bfloat16* out;
  uint32_t zero;
};

constexpr int SPIN_LIMIT = 1 << 17;

__device__ __forceinline__ void mbar_init(uint32_t bar, uint32_t count) {
  asm volatile("mbarrier.init.shared::cta.b64 [%0], %1;" ::"r"(bar), "r"(count) : "memory");
}
__device__ __forceinline__ void mbar_expect_tx(uint32_t bar, uint32_t bytes) {
  asm volatile("mbarrier.arrive.expect_tx.shared::cta.b64 _, [%0], %1;" ::"r"(bar), "r"(bytes) : "memory");
}
__device__ __forceinline__ void mbar_arrive(uint32_t bar) {
  asm volatile("mbarrier.arrive.shared::cta.b64 _, [%0];" ::"r"(bar) : "memory");
}
__device__ __forceinline__ void mbar_wait(uint32_t bar, uint32_t parity) {
  uint32_t ok;
  int spins = 0;
  do {
      asm volatile("{\n.reg .pred p;\nmbarrier.try_wait.parity.shared::cta.b64 p, [%1], %2;\nselp.b32 %0, 1, 0, p;\n}"
                   : "=r"(ok) : "r"(bar), "r"(parity) : "memory");
    if (++spins > SPIN_LIMIT) break;
  } while (!ok);
}
__device__ __forceinline__ unsigned flag_read(const unsigned* p) {
  unsigned v;
  asm volatile("ld.relaxed.gpu.global.u32 %0, [%1];" : "=r"(v) : "l"(p) : "memory");
  return v;
}
__device__ __forceinline__ void flag_poll(const unsigned* p, unsigned target) {
  unsigned v;
  int spins = 0;
  do {
    asm volatile("ld.relaxed.gpu.global.u32 %0, [%1];" : "=r"(v) : "l"(p) : "memory");
    if (++spins > SPIN_LIMIT) break;
  } while ((int)(v - target) < 0);
}
__device__ __forceinline__ void flag_wait(const unsigned* p, unsigned target) {
  flag_poll(p, target);
}
__device__ __forceinline__ void flag_signal(unsigned* p, int n, int lane) {
  if (lane == 0) asm volatile("fence.release.gpu;" ::: "memory");
  __syncwarp();
  if (lane < n) asm volatile("red.relaxed.gpu.global.add.u32 [%0], 1;" ::"l"(p + 32 * lane) : "memory");
}
__device__ __forceinline__ void flag_bump(unsigned* p) {
  asm volatile("red.relaxed.gpu.global.add.u32 [%0], 1;" ::"l"(p) : "memory");
}
__device__ __forceinline__ void fence_async_smem() { asm volatile("fence.proxy.async.shared::cta;" ::: "memory"); }
__device__ __forceinline__ void wg_sync(int id) { asm volatile("bar.sync %0, 128;" ::"r"(id) : "memory"); }

__device__ __forceinline__ void tma_2d(uint32_t dst, const CUtensorMap* tm, int c0, int c1, uint32_t bar) {
  asm volatile("cp.async.bulk.tensor.2d.shared::cluster.global.mbarrier::complete_tx::bytes [%0], [%1, {%3, %4}], [%2];"
               ::"r"(dst), "l"(tm), "r"(bar), "r"(c0), "r"(c1) : "memory");
}
__device__ __forceinline__ void tma_3d(uint32_t dst, const CUtensorMap* tm, int c0, int c1, int c2, uint32_t bar) {
  asm volatile("cp.async.bulk.tensor.3d.shared::cluster.global.mbarrier::complete_tx::bytes [%0], [%1, {%3, %4, %5}], [%2];"
               ::"r"(dst), "l"(tm), "r"(bar), "r"(c0), "r"(c1), "r"(c2) : "memory");
}
__device__ __forceinline__ void bulk_load(uint32_t dst, const void* src, uint32_t bytes, uint32_t bar) {
  asm volatile("cp.async.bulk.shared::cluster.global.mbarrier::complete_tx::bytes [%0], [%1], %2, [%3];"
               ::"r"(dst), "l"(src), "r"(bytes), "r"(bar) : "memory");
}
__device__ __forceinline__ void bulk_store(void* dst, uint32_t src, uint32_t bytes) {
  asm volatile("cp.async.bulk.global.shared::cta.bulk_group [%0], [%1], %2;" ::"l"(dst), "r"(src), "r"(bytes) : "memory");
}
__device__ __forceinline__ void bulk_wait_read() {
  asm volatile("cp.async.bulk.commit_group;\ncp.async.bulk.wait_group.read 0;" ::: "memory");
}

__device__ __forceinline__ void publish(void* dst, uint32_t src, uint32_t bytes, uint32_t bar) {
  bulk_store(dst, src, bytes);
  bulk_wait_read();
  bulk_load(src, dst, bytes, bar);
}

__device__ __forceinline__ void wg_fence() { asm volatile("wgmma.fence.sync.aligned;" ::: "memory"); }
__device__ __forceinline__ void wg_commit() { asm volatile("wgmma.commit_group.sync.aligned;" ::: "memory"); }
template <int N> __device__ __forceinline__ void wg_wait() { asm volatile("wgmma.wait_group.sync.aligned %0;" ::"n"(N) : "memory"); }
__device__ __forceinline__ uint32_t desc_lo(uint32_t addr, uint32_t lbo) { return ((addr & 0x3FFFF) >> 4) | ((lbo >> 4) << 16); }
constexpr uint32_t desc_hi(uint32_t sbo, uint32_t swz) { return (sbo >> 4) | (swz << 30); }
constexpr uint32_t HI_SW128 = desc_hi(1024, 1), HI_SW64 = desc_hi(512, 2), HI_SW32 = desc_hi(256, 3), HI_NONE = desc_hi(128, 0);
template <int N> __device__ __forceinline__ void pin(float* d) {
#pragma unroll
  for (int i = 0; i < N; i++) asm volatile("" : "+f"(d[i])::"memory");
}

__device__ __forceinline__ uint32_t lds32(uint32_t a) {
  uint32_t v;
  asm volatile("ld.volatile.shared.u32 %0, [%1];" : "=r"(v) : "r"(a) : "memory");
  return v;
}
__device__ __forceinline__ uint2 ldg64(const void* a) {
  uint2 v;
  asm volatile("ld.global.nc.v2.u32 {%0, %1}, [%2];" : "=r"(v.x), "=r"(v.y) : "l"(a) : "memory");
  return v;
}
__device__ __forceinline__ void ldsm4(uint32_t* r, uint32_t a) {
  asm volatile("ldmatrix.sync.aligned.m8n8.x4.shared.b16 {%0, %1, %2, %3}, [%4];"
               : "=r"(r[0]), "=r"(r[1]), "=r"(r[2]), "=r"(r[3]) : "r"(a) : "memory");
}
__device__ __forceinline__ void ldsm4t(uint32_t* r, uint32_t a) {
  asm volatile("ldmatrix.sync.aligned.m8n8.x4.trans.shared.b16 {%0, %1, %2, %3}, [%4];"
               : "=r"(r[0]), "=r"(r[1]), "=r"(r[2]), "=r"(r[3]) : "r"(a) : "memory");
}
__device__ __forceinline__ uint2 lds64(uint32_t a) {
  uint2 v;
  asm volatile("ld.shared.v2.u32 {%0, %1}, [%2];" : "=r"(v.x), "=r"(v.y) : "r"(a) : "memory");
  return v;
}
__device__ __forceinline__ uint4 lds128(uint32_t a) {
  uint4 v;
  asm volatile("ld.shared.v4.u32 {%0, %1, %2, %3}, [%4];" : "=r"(v.x), "=r"(v.y), "=r"(v.z), "=r"(v.w) : "r"(a) : "memory");
  return v;
}
__device__ __forceinline__ void sts128(uint32_t a, uint32_t x, uint32_t y, uint32_t z, uint32_t w) {
  asm volatile("st.shared.v4.u32 [%0], {%1, %2, %3, %4};" ::"r"(a), "r"(x), "r"(y), "r"(z), "r"(w) : "memory");
}
__device__ __forceinline__ void stsm4(uint32_t a, const uint32_t* r) {
  asm volatile("stmatrix.sync.aligned.m8n8.x4.shared.b16 [%0], {%1, %2, %3, %4};" ::"r"(a), "r"(r[0]), "r"(r[1]), "r"(r[2]), "r"(r[3]) : "memory");
}
__device__ __forceinline__ uint32_t pack2(float lo, float hi) {
  uint32_t r;
  asm("cvt.rn.bf16x2.f32 %0, %1, %2;" : "=r"(r) : "f"(hi), "f"(lo));
  return r;
}
__device__ __forceinline__ uint32_t movm(uint32_t a) {
  uint32_t d;
  asm volatile("movmatrix.sync.aligned.m8n8.trans.b16 %0, %1;" : "=r"(d) : "r"(a));
  return d;
}
__device__ __forceinline__ uint32_t bmul(uint32_t a, uint32_t b) {
  uint32_t d;
  asm("mul.rn.bf16x2 %0, %1, %2;" : "=r"(d) : "r"(a), "r"(b));
  return d;
}
__device__ __forceinline__ uint32_t badd(uint32_t a, uint32_t b) {
  uint32_t d;
  asm("add.rn.bf16x2 %0, %1, %2;" : "=r"(d) : "r"(a), "r"(b));
  return d;
}
__device__ __forceinline__ uint32_t bfma(uint32_t a, uint32_t b, uint32_t c) {
  uint32_t d;
  asm("fma.rn.bf16x2 %0, %1, %2, %3;" : "=r"(d) : "r"(a), "r"(b), "r"(c));
  return d;
}
__device__ __forceinline__ float bf_lo(uint32_t x) { return __uint_as_float(x << 16); }
__device__ __forceinline__ float bf_hi(uint32_t x) { return __uint_as_float(x & 0xFFFF0000u); }
__device__ __forceinline__ float ex2(float x) {
  float y;
  asm("ex2.approx.ftz.f32 %0, %1;" : "=f"(y) : "f"(x));
  return y;
}
__device__ __forceinline__ float rcp(float x) {
  float y;
  asm("rcp.approx.ftz.f32 %0, %1;" : "=f"(y) : "f"(x));
  return y;
}
__device__ __forceinline__ void mma16816(float* d, uint32_t a0, uint32_t a1, uint32_t a2, uint32_t a3, uint32_t b0, uint32_t b1) {
  asm volatile("mma.sync.aligned.m16n8k16.row.col.f32.bf16.bf16.f32 {%0, %1, %2, %3}, {%4, %5, %6, %7}, {%8, %9}, {%0, %1, %2, %3};"
               : "+f"(d[0]), "+f"(d[1]), "+f"(d[2]), "+f"(d[3])
               : "r"(a0), "r"(a1), "r"(a2), "r"(a3), "r"(b0), "r"(b1));
}
__device__ __forceinline__ void mma1688(float* d, uint32_t a0, uint32_t a1, uint32_t b0) {
  asm volatile("mma.sync.aligned.m16n8k8.row.col.f32.bf16.bf16.f32 {%0, %1, %2, %3}, {%4, %5}, {%6}, {%0, %1, %2, %3};"
               : "+f"(d[0]), "+f"(d[1]), "+f"(d[2]), "+f"(d[3])
               : "r"(a0), "r"(a1), "r"(b0));
}

template <int N> struct WgRS;
template <int N> struct WgSST;
template <> struct WgRS<32> {
  template <uint32_t HB>
  static __device__ __forceinline__ void mma(float* d, const uint32_t* a, uint32_t db) {
    asm volatile("{\n.reg .pred p;\n.reg .b64 db;\nsetp.ne.b32 p, %22, 0;\n"
      "mov.b64 db, {%20, %21};\n"
      "wgmma.mma_async.sync.aligned.m64n32k16.f32.bf16.bf16 {"
      "%0, %1, %2, %3, %4, %5, %6, %7, %8, %9, %10, %11, %12, %13, %14, %15"
      "}, {%16, %17, %18, %19}, db, p, 1, 1, 1;\n}\n"
      : "+f"(d[0]), "+f"(d[1]), "+f"(d[2]), "+f"(d[3]), "+f"(d[4]), "+f"(d[5]), "+f"(d[6]), "+f"(d[7]),
        "+f"(d[8]), "+f"(d[9]), "+f"(d[10]), "+f"(d[11]), "+f"(d[12]), "+f"(d[13]), "+f"(d[14]), "+f"(d[15])
      : "r"(a[0]), "r"(a[1]), "r"(a[2]), "r"(a[3]), "r"(db), "n"(HB), "n"(1));
  }
  template <uint32_t HB>
  static __device__ __forceinline__ void set(float* d, const uint32_t* a, uint32_t db) {
    asm volatile("{\n.reg .pred p;\n.reg .b64 db;\nsetp.ne.b32 p, %22, 0;\n"
      "mov.b64 db, {%20, %21};\n"
      "wgmma.mma_async.sync.aligned.m64n32k16.f32.bf16.bf16 {"
      "%0, %1, %2, %3, %4, %5, %6, %7, %8, %9, %10, %11, %12, %13, %14, %15"
      "}, {%16, %17, %18, %19}, db, p, 1, 1, 1;\n}\n"
      : "=f"(d[0]), "=f"(d[1]), "=f"(d[2]), "=f"(d[3]), "=f"(d[4]), "=f"(d[5]), "=f"(d[6]), "=f"(d[7]),
        "=f"(d[8]), "=f"(d[9]), "=f"(d[10]), "=f"(d[11]), "=f"(d[12]), "=f"(d[13]), "=f"(d[14]), "=f"(d[15])
      : "r"(a[0]), "r"(a[1]), "r"(a[2]), "r"(a[3]), "r"(db), "n"(HB), "n"(0));
  }
};
template <> struct WgRS<64> {
  template <uint32_t HB>
  static __device__ __forceinline__ void mma(float* d, const uint32_t* a, uint32_t db) {
    asm volatile("{\n.reg .pred p;\n.reg .b64 db;\nsetp.ne.b32 p, %38, 0;\n"
      "mov.b64 db, {%36, %37};\n"
      "wgmma.mma_async.sync.aligned.m64n64k16.f32.bf16.bf16 {"
      "%0, %1, %2, %3, %4, %5, %6, %7, %8, %9, %10, %11, %12, %13, %14, %15, "
      "%16, %17, %18, %19, %20, %21, %22, %23, %24, %25, %26, %27, %28, %29, %30, %31"
      "}, {%32, %33, %34, %35}, db, p, 1, 1, 1;\n}\n"
      : "+f"(d[0]), "+f"(d[1]), "+f"(d[2]), "+f"(d[3]), "+f"(d[4]), "+f"(d[5]), "+f"(d[6]), "+f"(d[7]),
        "+f"(d[8]), "+f"(d[9]), "+f"(d[10]), "+f"(d[11]), "+f"(d[12]), "+f"(d[13]), "+f"(d[14]), "+f"(d[15]),
        "+f"(d[16]), "+f"(d[17]), "+f"(d[18]), "+f"(d[19]), "+f"(d[20]), "+f"(d[21]), "+f"(d[22]), "+f"(d[23]),
        "+f"(d[24]), "+f"(d[25]), "+f"(d[26]), "+f"(d[27]), "+f"(d[28]), "+f"(d[29]), "+f"(d[30]), "+f"(d[31])
      : "r"(a[0]), "r"(a[1]), "r"(a[2]), "r"(a[3]), "r"(db), "n"(HB), "n"(1));
  }
  template <uint32_t HB>
  static __device__ __forceinline__ void set(float* d, const uint32_t* a, uint32_t db) {
    asm volatile("{\n.reg .pred p;\n.reg .b64 db;\nsetp.ne.b32 p, %38, 0;\n"
      "mov.b64 db, {%36, %37};\n"
      "wgmma.mma_async.sync.aligned.m64n64k16.f32.bf16.bf16 {"
      "%0, %1, %2, %3, %4, %5, %6, %7, %8, %9, %10, %11, %12, %13, %14, %15, "
      "%16, %17, %18, %19, %20, %21, %22, %23, %24, %25, %26, %27, %28, %29, %30, %31"
      "}, {%32, %33, %34, %35}, db, p, 1, 1, 1;\n}\n"
      : "=f"(d[0]), "=f"(d[1]), "=f"(d[2]), "=f"(d[3]), "=f"(d[4]), "=f"(d[5]), "=f"(d[6]), "=f"(d[7]),
        "=f"(d[8]), "=f"(d[9]), "=f"(d[10]), "=f"(d[11]), "=f"(d[12]), "=f"(d[13]), "=f"(d[14]), "=f"(d[15]),
        "=f"(d[16]), "=f"(d[17]), "=f"(d[18]), "=f"(d[19]), "=f"(d[20]), "=f"(d[21]), "=f"(d[22]), "=f"(d[23]),
        "=f"(d[24]), "=f"(d[25]), "=f"(d[26]), "=f"(d[27]), "=f"(d[28]), "=f"(d[29]), "=f"(d[30]), "=f"(d[31])
      : "r"(a[0]), "r"(a[1]), "r"(a[2]), "r"(a[3]), "r"(db), "n"(HB), "n"(0));
  }
};
template <> struct WgSST<48> {
  template <uint32_t HA, uint32_t HB>
  static __device__ __forceinline__ void mma(float* d, uint32_t da, uint32_t db, int sc) {
    asm volatile("{\n.reg .pred p;\n.reg .b64 da, db;\nsetp.ne.b32 p, %28, 0;\n"
      "mov.b64 da, {%24, %25};\nmov.b64 db, {%26, %27};\n"
      "wgmma.mma_async.sync.aligned.m64n48k16.f32.bf16.bf16 {"
      "%0, %1, %2, %3, %4, %5, %6, %7, %8, %9, %10, %11, %12, %13, %14, %15, "
      "%16, %17, %18, %19, %20, %21, %22, %23"
      "}, da, db, p, 1, 1, 0, 1;\n}\n"
      : "+f"(d[0]), "+f"(d[1]), "+f"(d[2]), "+f"(d[3]), "+f"(d[4]), "+f"(d[5]), "+f"(d[6]), "+f"(d[7]),
        "+f"(d[8]), "+f"(d[9]), "+f"(d[10]), "+f"(d[11]), "+f"(d[12]), "+f"(d[13]), "+f"(d[14]), "+f"(d[15]),
        "+f"(d[16]), "+f"(d[17]), "+f"(d[18]), "+f"(d[19]), "+f"(d[20]), "+f"(d[21]), "+f"(d[22]), "+f"(d[23])
      : "r"(da), "n"(HA), "r"(db), "n"(HB), "r"(sc));
  }
};
template <> struct WgSST<80> {
  template <uint32_t HA, uint32_t HB>
  static __device__ __forceinline__ void mma(float* d, uint32_t da, uint32_t db, int sc) {
    asm volatile("{\n.reg .pred p;\n.reg .b64 da, db;\nsetp.ne.b32 p, %44, 0;\n"
      "mov.b64 da, {%40, %41};\nmov.b64 db, {%42, %43};\n"
      "wgmma.mma_async.sync.aligned.m64n80k16.f32.bf16.bf16 {"
      "%0, %1, %2, %3, %4, %5, %6, %7, %8, %9, %10, %11, %12, %13, %14, %15, "
      "%16, %17, %18, %19, %20, %21, %22, %23, %24, %25, %26, %27, %28, %29, %30, %31, "
      "%32, %33, %34, %35, %36, %37, %38, %39"
      "}, da, db, p, 1, 1, 0, 1;\n}\n"
      : "+f"(d[0]), "+f"(d[1]), "+f"(d[2]), "+f"(d[3]), "+f"(d[4]), "+f"(d[5]), "+f"(d[6]), "+f"(d[7]),
        "+f"(d[8]), "+f"(d[9]), "+f"(d[10]), "+f"(d[11]), "+f"(d[12]), "+f"(d[13]), "+f"(d[14]), "+f"(d[15]),
        "+f"(d[16]), "+f"(d[17]), "+f"(d[18]), "+f"(d[19]), "+f"(d[20]), "+f"(d[21]), "+f"(d[22]), "+f"(d[23]),
        "+f"(d[24]), "+f"(d[25]), "+f"(d[26]), "+f"(d[27]), "+f"(d[28]), "+f"(d[29]), "+f"(d[30]), "+f"(d[31]),
        "+f"(d[32]), "+f"(d[33]), "+f"(d[34]), "+f"(d[35]), "+f"(d[36]), "+f"(d[37]), "+f"(d[38]), "+f"(d[39])
      : "r"(da), "n"(HA), "r"(db), "n"(HB), "r"(sc));
  }
};
template <> struct WgSST<192> {
  template <uint32_t HA, uint32_t HB>
  static __device__ __forceinline__ void mma(float* d, uint32_t da, uint32_t db, int sc) {
    asm volatile("{\n.reg .pred p;\n.reg .b64 da, db;\nsetp.ne.b32 p, %100, 0;\n"
      "mov.b64 da, {%96, %97};\nmov.b64 db, {%98, %99};\n"
      "wgmma.mma_async.sync.aligned.m64n192k16.f32.bf16.bf16 {"
      "%0, %1, %2, %3, %4, %5, %6, %7, %8, %9, %10, %11, %12, %13, %14, %15, "
      "%16, %17, %18, %19, %20, %21, %22, %23, %24, %25, %26, %27, %28, %29, %30, %31, "
      "%32, %33, %34, %35, %36, %37, %38, %39, %40, %41, %42, %43, %44, %45, %46, %47, "
      "%48, %49, %50, %51, %52, %53, %54, %55, %56, %57, %58, %59, %60, %61, %62, %63, "
      "%64, %65, %66, %67, %68, %69, %70, %71, %72, %73, %74, %75, %76, %77, %78, %79, "
      "%80, %81, %82, %83, %84, %85, %86, %87, %88, %89, %90, %91, %92, %93, %94, %95"
      "}, da, db, p, 1, 1, 0, 1;\n}\n"
      : "+f"(d[0]), "+f"(d[1]), "+f"(d[2]), "+f"(d[3]), "+f"(d[4]), "+f"(d[5]), "+f"(d[6]), "+f"(d[7]),
        "+f"(d[8]), "+f"(d[9]), "+f"(d[10]), "+f"(d[11]), "+f"(d[12]), "+f"(d[13]), "+f"(d[14]), "+f"(d[15]),
        "+f"(d[16]), "+f"(d[17]), "+f"(d[18]), "+f"(d[19]), "+f"(d[20]), "+f"(d[21]), "+f"(d[22]), "+f"(d[23]),
        "+f"(d[24]), "+f"(d[25]), "+f"(d[26]), "+f"(d[27]), "+f"(d[28]), "+f"(d[29]), "+f"(d[30]), "+f"(d[31]),
        "+f"(d[32]), "+f"(d[33]), "+f"(d[34]), "+f"(d[35]), "+f"(d[36]), "+f"(d[37]), "+f"(d[38]), "+f"(d[39]),
        "+f"(d[40]), "+f"(d[41]), "+f"(d[42]), "+f"(d[43]), "+f"(d[44]), "+f"(d[45]), "+f"(d[46]), "+f"(d[47]),
        "+f"(d[48]), "+f"(d[49]), "+f"(d[50]), "+f"(d[51]), "+f"(d[52]), "+f"(d[53]), "+f"(d[54]), "+f"(d[55]),
        "+f"(d[56]), "+f"(d[57]), "+f"(d[58]), "+f"(d[59]), "+f"(d[60]), "+f"(d[61]), "+f"(d[62]), "+f"(d[63]),
        "+f"(d[64]), "+f"(d[65]), "+f"(d[66]), "+f"(d[67]), "+f"(d[68]), "+f"(d[69]), "+f"(d[70]), "+f"(d[71]),
        "+f"(d[72]), "+f"(d[73]), "+f"(d[74]), "+f"(d[75]), "+f"(d[76]), "+f"(d[77]), "+f"(d[78]), "+f"(d[79]),
        "+f"(d[80]), "+f"(d[81]), "+f"(d[82]), "+f"(d[83]), "+f"(d[84]), "+f"(d[85]), "+f"(d[86]), "+f"(d[87]),
        "+f"(d[88]), "+f"(d[89]), "+f"(d[90]), "+f"(d[91]), "+f"(d[92]), "+f"(d[93]), "+f"(d[94]), "+f"(d[95])
      : "r"(da), "n"(HA), "r"(db), "n"(HB), "r"(sc));
  }
};

struct FftConst {
  uint32_t f[2][4], fi[4][4];
  uint32_t ta[2][2], tb[2][2];
};
__device__ __forceinline__ void cis(int m, float scale, float& c, float& s) {
  const float a = (float)m * (-6.283185307179586f * scale);
  c = __cosf(a);
  s = __sinf(a);
}
__device__ __forceinline__ void fft_tables(uint32_t (&v)[12], int tw) {
  const int row = tw >> 2, ch = tw & 3;
#pragma unroll
  for (int i = 0; i < 4; i++) {
    float c[2], s[2], x[2];
#pragma unroll
    for (int e = 0; e < 2; e++) {
      cis((((32 * (8 * ch + 2 * i + e) + 15) * (4 * row - 63) + 2048) & 4095) - 2048, 1.f / 4096, c[e], s[e]);
      float gc, gs;
      cis((((row & 15) * (8 * (ch & 1) + 2 * i + e) + 8) & 15) - 8, 1.f / 16, gc, gs);
      x[e] = (row >> 4) == (ch >> 1) ? gc : (ch >> 1) ? gs : -gs;
    }
    v[i] = pack2(c[0] * 0.125f, c[1] * 0.125f);
    v[4 + i] = pack2(s[0] * 0.125f, s[1] * 0.125f);
    v[8 + i] = pack2(x[0], x[1]);
  }
#pragma unroll
  for (int i = 0; i < 12; i++) asm volatile("" : "+r"(v[i]));
}
__device__ __forceinline__ void fft_tables_store(const uint32_t (&v)[12], uint32_t sb, int tw) {
  const int row = tw >> 2;
  const uint32_t x = ((tw ^ (row >> 1)) & 3) << 4, a = sb + OFF_FT + (16 * (row >> 3) + (row & 7)) * 64 + x;
  sts128(a, v[0], v[1], v[2], v[3]);
  sts128(a + 512, v[4], v[5], v[6], v[7]);
  sts128(sb + OFF_GT + row * 64 + x, v[8], v[9], v[10], v[11]);
}
__device__ __forceinline__ void fft_twiddles(uint32_t (&v)[2], int tw) {
  float a[2], s[2];
#pragma unroll
  for (int i = 0; i < 2; i++) {
    float c;
    cis((2 * (2 * (tw & 3) + i) - 15) * (4 * (tw >> 2) - 63), 1.f / 4096, c, s[i]);
    a[i] = __fdividef(-s[i], 1.f + c);
  }
  v[0] = pack2(a[0], a[1]);
  v[1] = pack2(s[0], s[1]);
  asm volatile("" : "+r"(v[0]), "+r"(v[1]));
}
__device__ __forceinline__ void fft_matrices(FftConst& k, uint32_t sb, int w, int lane) {
  const uint32_t x = (lane >> 1) & 3;
  const uint2 t0 = lds64(sb + OFF_TT + 256 * w + 8 * lane), t1 = lds64(sb + OFF_TT + 256 * w + 8 * (lane ^ 3));
  k.ta[0][0] = t0.x;
  k.tb[0][0] = t0.y;
  k.ta[1][1] = __byte_perm(t1.x, 0, 0x1032);
  k.tb[1][1] = __byte_perm(t1.y, 0, 0x1032);
#pragma unroll
  for (int j = 0; j < 2; j++) {
    k.ta[1 - j][j] = k.ta[j][j] ^ 0x80008000u;
    k.tb[1 - j][j] = k.tb[j][j] ^ 0x80008000u;
    asm volatile("" : "+r"(k.ta[0][j]), "+r"(k.tb[0][j]), "+r"(k.ta[1][j]), "+r"(k.tb[1][j]));
  }
#pragma unroll
  for (int i = 0; i < 2; i++) {
    ldsm4(k.f[i], sb + OFF_FT + (16 * w + (lane & 15)) * 64 + (((2 * i + (lane >> 4)) ^ x) << 4));
    ldsm4t(k.fi[i], sb + OFF_FT + (32 * i + lane) * 64 + ((w ^ x) << 4));
#pragma unroll
    for (int j = 0; j < 4; j++) {
      k.fi[2 + i][j] = (j & 1) ? k.fi[i][j - 1] ^ 0x80008000u : k.fi[i][j + 1];
      asm volatile("" : "+r"(k.fi[2 + i][j]));
    }
  }
}
__device__ __forceinline__ void rot(uint32_t& x, uint32_t& y, uint32_t a, uint32_t b) {
  x = bfma(a, y, x);
  y = bfma(b, x, y);
  x = bfma(a, y, x);
}
__device__ __forceinline__ void twiddle_fwd(uint32_t (&a)[4][4], float* d, const FftConst& k) {
#pragma unroll
  for (int q = 0; q < 4; q++)
#pragma unroll
    for (int j = 0; j < 2; j++) {
      const float* x = d + 8 * q + 4 * j;
      uint32_t re = pack2(x[0], x[1]), im = pack2(x[2], x[3]);
      rot(re, im, k.ta[0][j], k.tb[0][j]);
      a[q & 2][2 * j + (q & 1)] = re;
      a[(q & 2) + 1][2 * j + (q & 1)] = im;
    }
}
__device__ __forceinline__ void g_step(float* d, const uint32_t (&a)[4][4], uint32_t dre, uint32_t dim) {
  WgRS<32>::set<HI_SW64>(d, a[0], dre);
  WgRS<32>::set<HI_SW64>(d + 16, a[2], dre);
  WgRS<32>::mma<HI_SW64>(d, a[1], dim);
  WgRS<32>::mma<HI_SW64>(d + 16, a[3], dim);
  wg_commit();
}

__device__ __forceinline__ void products(uint32_t (&a)[4][4], const float* H, const float* U, int p) {
#pragma unroll
  for (int j = 0; j < 2; j++)
#pragma unroll
    for (int m = 2 * p; m < 2 * p + 2; m++) {
      float pr[2], pi[2];
#pragma unroll
      for (int x = 0; x < 2; x++)
#pragma unroll
        for (int q = 0; q <= m; q++) {
          const int ih = 16 * (q >> 1) + 2 * (q & 1) + 4 * j + x, iu = 16 * ((m - q) >> 1) + 2 * ((m - q) & 1) + 4 * j + x;
          pr[x] = q ? fmaf(H[ih], U[iu], pr[x]) : H[ih] * U[iu];
          pi[x] = q ? fmaf(H[ih], U[iu + 8], pi[x]) : H[ih] * U[iu + 8];
          pr[x] = fmaf(-H[ih + 8], U[iu + 8], pr[x]);
          pi[x] = fmaf(H[ih + 8], U[iu], pi[x]);
        }
      a[m & 2][2 * j + (m & 1)] = pack2(pr[0], pr[1]);
      a[(m & 2) + 1][2 * j + (m & 1)] = pack2(pi[0], pi[1]);
    }
}

__device__ __forceinline__ void conv_channel(const FftConst& k, uint32_t sb, int c, int wg, int w, int lane) {
  const uint32_t cb = sb + off_ch(c), bars = sb + OFF_BAR;
  const uint32_t du = desc_lo(cb, 1024), dg = desc_lo(sb + OFF_GT, 16), dz = desc_lo(cb + U_BYTES, 16);
  float U[32], H[32];
  uint32_t a[4][4], e[4][4];
  const float dv = __uint_as_float(lds32(sb + OFF_D + 4 * c));
  wg_fence();
  WgRS<64>::set<HI_SW32>(H, k.f[0], du + 256);
  WgRS<64>::mma<HI_SW32>(H, k.f[1], du + 256 + 32);
  wg_commit();
  wg_wait<0>();
  pin<32>(H);
  twiddle_fwd(a, H, k);
  mbar_wait(bars + 8 * (B_U + (c < 3 ? c : 3)), 0);
  TSM(w == 0 && c < 3, 7 + wg);
  wg_fence();
  WgRS<64>::set<HI_SW32>(U, k.f[0], du);
  WgRS<64>::mma<HI_SW32>(U, k.f[1], du + 32);
  wg_commit();
  g_step(H, a, dg, dg + 64);
  wg_wait<1>();
  pin<32>(U);
  twiddle_fwd(e, U, k);
  wg_fence();
  g_step(U, e, dg, dg + 64);
  wg_wait<0>();
  pin<32>(U);
  pin<32>(H);
#pragma unroll
  for (int j = 0; j < 4; j++) H[4 * (j >> 1) + (j & 1)] += dv;
  float V[32];
#pragma unroll
  for (int p = 0; p < 2; p++) {
    products(a, H, U, p);
    wg_fence();
    WgRS<32>::set<HI_SW64>(V + 16 * p, a[2 * p], dg + 64);
    WgRS<32>::mma<HI_SW64>(V + 16 * p, a[2 * p + 1], dg);
    wg_commit();
  }
  const uint32_t za = cb + U_BYTES + (8 * w + (lane & 7)) * 128 + (((lane >> 3) ^ (lane & 7)) << 4);
  const uint32_t ya = cb + (lane >> 4) * 1024 + (8 * w + (lane & 7)) * 32 + ((((lane >> 3) ^ (lane >> 2)) & 1) << 4);
  wg_sync(1 + wg);
#pragma unroll
  for (int p = 0; p < 2; p++) {
    if (p == 0) wg_wait<1>();
    else wg_wait<0>();
    pin<16>(V + 16 * p);
#pragma unroll
    for (int i = 0; i < 4; i++) {
      const int j = i & 1;
      const float* x = V + 16 * p + 4 * j + (i & 2);
      e[p][i] = pack2(x[8], x[9]);
      e[2 + p][i] = pack2(x[0], x[1]);
      rot(e[p][i], e[2 + p][i], k.ta[1][j], k.tb[1][j]);
    }
    stsm4(za ^ (64 * p), e[p]);
    stsm4((za ^ (64 * p)) + 4096, e[2 + p]);
  }
  fence_async_smem();
  wg_sync(1 + wg);
  wg_fence();
  WgRS<64>::set<HI_SW128>(H, k.fi[0], dz);
#pragma unroll
  for (int ks = 1; ks < 4; ks++) WgRS<64>::mma<HI_SW128>(H, k.fi[ks], dz + 128 * ks);
  wg_commit();
  wg_wait<0>();
  pin<32>(H);
  if (lane == 0) mbar_arrive(bars + 8 * B_CVD);
  TSIF(w == 0, 88 + c);
#pragma unroll
  for (int j = 0; j < 8; j++)
    a[j >> 2][j & 3] = j < 2 ? pack2(H[4 * j], H[4 * j + 1]) : pack2(H[4 * j] + H[4 * j - 6], H[4 * j + 1] + H[4 * j - 5]);
  stsm4(ya, a[0]);
  stsm4(ya + 2048, a[1]);
  fence_async_smem();
  __syncwarp();
}

__device__ __forceinline__ void prep_slab(uint4* res, const uint2* sw, uint32_t sb, int slab, int w, int lane) {
  const int t = lane & 3, tp = (lane & 7) >> 1, pos = 8 * tp + 2 * (((lane >> 3) + tp) & 3) + (lane & 1);
  const uint32_t base = sb + OFF_KVS + slab * KVS_BYTES + pos * 128;
  uint32_t kk[2][4][4], vv[2][4];
  mbar_wait(sb + OFF_BAR + 8 * (B_KV + slab), 0);
#pragma unroll
  for (int h = 0; h < 2; h++) {
#pragma unroll
    for (int j = 0; j < 4; j++) {
      const uint32_t a = base + 128 * j;
      ldsm4t(kk[h][j], a + (((w + 4 * h) ^ ((a >> 7) & 7)) << 4));
    }
    const uint32_t a = base + KVS_V;
    ldsm4t(vv[h], a + (((w + 4 * h) ^ ((a >> 7) & 7)) << 4));
  }
#pragma unroll
  for (int h = 0; h < 2; h++) {
    uint32_t (&k)[4][4] = kk[h];
    uint32_t (&v)[4] = vv[h];
    const uint32_t w0 = __byte_perm(sw[h].x, 0, 0x1010), w1 = __byte_perm(sw[h].x, 0, 0x3232);
    const uint32_t w2 = __byte_perm(sw[h].y, 0, 0x1010), w3 = __byte_perm(sw[h].y, 0, 0x3232);
#pragma unroll
    for (int m = 0; m < 4; m++)
      v[m] = bmul(badd(badd(badd(bmul(k[0][m], w3), bmul(k[1][m], w2)), bmul(k[2][m], w1)), bmul(k[3][m], w0)), v[m]);
    uint32_t a[4];
#pragma unroll
    for (int m = 0; m < 4; m++) a[m] = (t & 1) ? v[(m + 3) & 3] : v[m];
    res[h] = (t & 2) ? make_uint4(a[2], a[3], a[0], a[1]) : make_uint4(a[0], a[1], a[2], a[3]);
  }
}

__device__ __forceinline__ void prep_gate(const Params& p, uint32_t sb, int b, int w, int lane) {
  uint2 gw[5], x[4][5];
#pragma unroll
  for (int j = 0; j < 5; j++) gw[j] = ldg64(reinterpret_cast<const uint2*>(p.gate_w) + lane + 32 * j);
#pragma unroll
  for (int i = 0; i < 4; i++)
#pragma unroll
    for (int j = 0; j < 5; j++)
      x[i][j] = ldg64(reinterpret_cast<const uint2*>(p.q) + (16 * b + 4 * w + i) * (DIM / 4) + lane + 32 * j);
  float s[4];
#pragma unroll
  for (int i = 0; i < 4; i++) {
    s[i] = 0.f;
#pragma unroll
    for (int j = 0; j < 5; j++) {
      const uint32_t m0 = bmul(x[i][j].x, gw[j].x), m1 = bmul(x[i][j].y, gw[j].y);
      s[i] += (bf_lo(m0) + bf_hi(m0)) + (bf_lo(m1) + bf_hi(m1));
    }
  }
  const bool h = lane & 16, q = lane & 8;
  const float a = (h ? s[2] : s[0]) + __shfl_xor_sync(0xffffffffu, h ? s[0] : s[2], 16);
  const float c = (h ? s[3] : s[1]) + __shfl_xor_sync(0xffffffffu, h ? s[1] : s[3], 16);
  float z = (q ? c : a) + __shfl_xor_sync(0xffffffffu, q ? a : c, 8);
#pragma unroll
  for (int o = 4; o > 0; o >>= 1) z += __shfl_xor_sync(0xffffffffu, z, o);
  z = bf_lo(pack2(z, 0.f));
  z = bf_lo(pack2(__fdividef(1.f, 1.f + __expf(-z)), 0.f));
  mbar_wait(sb + OFF_BAR + 8 * B_S3, 0);
  if ((lane & 7) == 0) asm volatile("st.shared.f32 [%0], %1;" ::"r"(sb + OFF_GATE + 64 * (b & 7) + 16 * w + (lane >> 1)), "f"(z) : "memory");
  fence_async_smem();
}

__device__ __forceinline__ uint32_t bmax(uint32_t a, uint32_t b) {
  uint32_t d;
  asm("max.bf16x2 %0, %1, %2;" : "=r"(d) : "r"(a), "r"(b));
  return d;
}
__device__ __forceinline__ void softmax_two(const float (&l)[2][2], uint32_t& p0, uint32_t& p1) {
  constexpr float kScale = 0.22360679774997896f, kLog2e = 1.4426950408889634f;
  const uint32_t r0 = pack2(l[0][0], l[1][0]), r1 = pack2(l[0][1], l[1][1]);
  const uint32_t x0 = pack2(bf_lo(r0) * kScale, bf_hi(r0) * kScale), x1 = pack2(bf_lo(r1) * kScale, bf_hi(r1) * kScale);
  uint32_t m = bmax(x0, x1);
  m = bmax(m, __shfl_xor_sync(0xffffffffu, m, 1));
  m = bmax(m, __shfl_xor_sync(0xffffffffu, m, 2));
  const float m0 = bf_lo(m) * kLog2e, m1 = bf_hi(m) * kLog2e;
  p0 = pack2(ex2(bf_lo(x0) * kLog2e - m0), ex2(bf_lo(x1) * kLog2e - m0));
  p1 = pack2(ex2(bf_hi(x0) * kLog2e - m1), ex2(bf_hi(x1) * kLog2e - m1));
}

__device__ __forceinline__ void halo_read(uint32_t (&kpv)[10], uint32_t (&vpv)[10], uint32_t (&tg)[7], const uint4* hp) {
#pragma unroll
  for (int j = 0; j < 7; j++) {
    uint32_t x0, x1, x2;
    asm volatile("ld.relaxed.gpu.global.v4.u32 {%0, %1, %2, %3}, [%4];"
                 : "=r"(x0), "=r"(x1), "=r"(x2), "=r"(tg[j]) : "l"(hp + 32 * j) : "memory");
    if (j < 4) kpv[3 * j] = x0; else vpv[3 * j - 10] = x0;
    if (j < 3) kpv[3 * j + 1] = x1; else vpv[3 * j - 9] = x1;
    if (j < 3) kpv[3 * j + 2] = x2; else if (j < 6) vpv[3 * j - 8] = x2;
  }
}

template <int ROT>
__device__ __forceinline__ void pack_qkv(const float* acc, uint32_t (&qlo)[10], uint32_t (&qhi)[10], uint32_t (&klo)[10],
                                         uint32_t (&khi)[10], uint32_t (&vlo)[10], uint32_t (&vhi)[10]) {
#pragma unroll
  for (int j = 0; j < 10; j++) {
    const int x = (j + ROT) % 10, tq = x < 8 ? x : 16 + x, tk = x < 8 ? 8 + x : 18 + x, tv = x < 8 ? 16 + x : 20 + x;
    khi[j] = pack2(acc[4 * tk + 2], acc[4 * tk + 3]);
    vhi[j] = movm(pack2(acc[4 * tv + 2], acc[4 * tv + 3]));
    qlo[j] = pack2(acc[4 * tq], acc[4 * tq + 1]);
    qhi[j] = pack2(acc[4 * tq + 2], acc[4 * tq + 3]);
    klo[j] = pack2(acc[4 * tk], acc[4 * tk + 1]);
    vlo[j] = pack2(acc[4 * tv], acc[4 * tv + 1]);
    asm volatile("" : "+r"(khi[j]), "+r"(qlo[j]), "+r"(qhi[j]), "+r"(klo[j]), "+r"(vlo[j]));
  }
}

template <int ROT> __device__ __forceinline__ void halo_send(const float* acc, uint4* ho, uint32_t tag) {
#pragma unroll
  for (int j = 0; j < 7; j++) {
    uint32_t x[3];
#pragma unroll
    for (int e = 0; e < 3; e++) {
      const int i = 3 * j + e, y = (i % 10 + ROT) % 10, tk = y < 8 ? 8 + y : 18 + y, tv = y < 8 ? 16 + y : 20 + y;
      x[e] = i < 10 ? pack2(acc[4 * tk + 2], acc[4 * tk + 3]) : i < 20 ? movm(pack2(acc[4 * tv + 2], acc[4 * tv + 3])) : 0u;
    }
    asm volatile("st.relaxed.gpu.global.v4.u32 [%0], {%1, %2, %3, %4};" ::"l"(ho + 32 * j), "r"(x[0]), "r"(x[1]), "r"(x[2]), "r"(tag) : "memory");
  }
}

__device__ __forceinline__ void attention(float* acc, uint32_t sb, int b, int par, int w, int lane, uint32_t tag) {
  const int g = lane >> 2, t = lane & 3;
  uint32_t klo[10], khi[10], vlo[10], vhi[10], qlo[10], qhi[10], kpv[10], vpv[10];
  if (w == 3 && b < NCTA - 8) {
    uint4* ho = g_halo + (b * 2 + par) * 224 + lane;
    if (tail_first(b & 7)) halo_send<8>(acc, ho, tag);
    else halo_send<0>(acc, ho, tag);
    TSIF(par == 0, 76);
    pin<120>(acc);
  }
  if (tail_first(b & 7)) pack_qkv<8>(acc, qlo, qhi, klo, khi, vlo, vhi);
  else pack_qkv<0>(acc, qlo, qhi, klo, khi, vlo, vhi);
  const uint32_t xa = sb + OFF_KVX + (par * 3) * 2560 + lane * 16;
  if (w < 3) {
    sts128(xa + w * 2560, khi[0], khi[1], khi[2], khi[3]);
    sts128(xa + w * 2560 + 512, khi[4], khi[5], khi[6], khi[7]);
    sts128(xa + w * 2560 + 1024, khi[8], khi[9], vhi[0], vhi[1]);
    sts128(xa + w * 2560 + 1536, vhi[2], vhi[3], vhi[4], vhi[5]);
    sts128(xa + w * 2560 + 2048, vhi[6], vhi[7], vhi[8], vhi[9]);
  }
  TSIF(par == 0 && w == 1, 64);
#pragma unroll
  for (int j = 0; j < 10; j++) vlo[j] = movm(vlo[j]);
  const bool far0 = 2 * t > g, far1 = 2 * t + 1 > g;
  const uint32_t mfar = (far0 ? 0x0000FFFFu : 0u) | (far1 ? 0xFFFF0000u : 0u);
  float slo[4][2], lg[2][2];
  uint32_t phi[4], plo[4], qml[4], qmh[4];
  const bool nohist = (w == 0) && (b < 8);
  const uint4* hp = g_halo + ((b - 8) * 2 + par) * 224 + lane;
  uint32_t tg[7];
#pragma unroll
  for (int h = 0; h < 4; h++) {
    if (h == HR_AT && w == 0 && !nohist) halo_read(kpv, vpv, tg, hp);
    const int f = h == 0 ? 0 : h == 1 ? 3 : h == 2 ? 5 : 8, hf = h < 2 ? 2 : 7;
    const bool mine = (h & 1) ? t >= 2 : t < 2;
    qml[h] = mine ? qlo[hf] : 0u;
    qmh[h] = mine ? qhi[hf] : 0u;
    float a[4] = {0.f, 0.f, 0.f, 0.f}, c[4] = {0.f, 0.f, 0.f, 0.f};
    mma16816(a, qlo[f], qhi[f], qlo[f + 1], qhi[f + 1], klo[f], klo[f + 1]);
    mma16816(c, qlo[f], qhi[f], qlo[f + 1], qhi[f + 1], khi[f], khi[f + 1]);
    mma1688(a, qml[h], qmh[h], klo[hf]);
    mma1688(c, qml[h], qmh[h], khi[hf]);
    slo[h][0] = a[0];
    slo[h][1] = a[1];
    lg[h & 1][0] = far0 ? a[2] : c[2];
    lg[h & 1][1] = far1 ? a[3] : c[3];
    if (h & 1) softmax_two(lg, phi[h - 1], phi[h]);
  }
  if (HR_AT == 4 && w == 0 && !nohist) halo_read(kpv, vpv, tg, hp);
  TSIF(par == 0 && w == 1, 65);
  wg_sync(1 + par);
  TSIF(par == 0 && w == 1, 66);
  if (w > 0) {
    const uint4 v0 = lds128(xa + (w - 1) * 2560), v1 = lds128(xa + (w - 1) * 2560 + 512), v2 = lds128(xa + (w - 1) * 2560 + 1024);
    const uint4 v3 = lds128(xa + (w - 1) * 2560 + 1536), v4 = lds128(xa + (w - 1) * 2560 + 2048);
    kpv[0] = v0.x; kpv[1] = v0.y; kpv[2] = v0.z; kpv[3] = v0.w; kpv[4] = v1.x; kpv[5] = v1.y; kpv[6] = v1.z; kpv[7] = v1.w;
    kpv[8] = v2.x; kpv[9] = v2.y; vpv[0] = v2.z; vpv[1] = v2.w; vpv[2] = v3.x; vpv[3] = v3.y; vpv[4] = v3.z; vpv[5] = v3.w;
    vpv[6] = v4.x; vpv[7] = v4.y; vpv[8] = v4.z; vpv[9] = v4.w;
  } else if (nohist) {
#pragma unroll
    for (int j = 0; j < 10; j++) kpv[j] = vpv[j] = 0u;
  } else if (HR_AT == 5) {
    TSIF(par == 0, 77);
    halo_read(kpv, vpv, tg, hp);
  }
  if (w == 0 && !nohist) {
    int spins = 0;
    while (true) {
      bool ok = true;
#pragma unroll
      for (int j = 0; j < 7; j++) ok = ok && tg[j] == tag;
      if (__all_sync(0xffffffffu, ok) || ++spins > SPIN_LIMIT) break;
      halo_read(kpv, vpv, tg, hp);
    }
    TSIF(par == 0, 79);
  }
#pragma unroll
  for (int h = 0; h < 4; h++) {
    const int f = h == 0 ? 0 : h == 1 ? 3 : h == 2 ? 5 : 8, hf = h < 2 ? 2 : 7;
    float a[4] = {0.f, 0.f, 0.f, 0.f};
    mma16816(a, qlo[f], qhi[f], qlo[f + 1], qhi[f + 1], kpv[f], kpv[f + 1]);
    mma1688(a, qml[h], qmh[h], kpv[hf]);
    const float ninf = __int_as_float(0xff800000);
    lg[h & 1][0] = far0 ? (nohist ? ninf : a[0]) : slo[h][0];
    lg[h & 1][1] = far1 ? (nohist ? ninf : a[1]) : slo[h][1];
    if (h & 1) softmax_two(lg, plo[h - 1], plo[h]);
  }
  TSIF(par == 0 && w <= 1, 67 + w);
  uint32_t ov[20];
#pragma unroll
  for (int hp = 0; hp < 2; hp++) {
    const int hf = hp ? 7 : 2;
    float sh[4] = {0.f, 0.f, 0.f, 0.f}, i0 = 0.f, i1 = 0.f;
#pragma unroll
    for (int e = 0; e < 2; e++) {
      const int h = 2 * hp + e, f = h == 0 ? 0 : h == 1 ? 3 : h == 2 ? 5 : 8;
      const uint32_t a0 = plo[h] & mfar, a2 = plo[h] & ~mfar, a3 = phi[h] & mfar, c1 = phi[h] & ~mfar;
      float sum[4] = {0.f, 0.f, 0.f, 0.f};
      mma1688(sum, plo[h], phi[h], 0x3F803F80u);
      const float r0 = rcp(sum[0]), r1 = rcp(sum[2]);
#pragma unroll
      for (int j = f; j < f + 2; j++) {
        float o[4] = {0.f, 0.f, 0.f, 0.f};
        mma16816(o, a0, 0u, a2, a3, vpv[j], vlo[j]);
        mma1688(o, 0u, c1, vhi[j]);
        ov[2 * j] = pack2(o[0] * r0, o[1] * r0);
        ov[2 * j + 1] = pack2(o[2] * r1, o[3] * r1);
      }
      const bool mine = e ? g >= 4 : g < 4;
      mma16816(sh, a0, 0u, a2, a3, mine ? vpv[hf] : 0u, mine ? vlo[hf] : 0u);
      mma1688(sh, 0u, c1, mine ? vhi[hf] : 0u);
      if (e == 0 || t >= 2) {
        i0 = r0;
        i1 = r1;
      }
    }
    ov[2 * hf] = pack2(sh[0] * i0, sh[1] * i0);
    ov[2 * hf + 1] = pack2(sh[2] * i1, sh[3] * i1);
  }
  TS(32 + 4 * par + w);
  mbar_wait(sb + OFF_BAR + 8 * B_P1, 0);
  const uint32_t oa = sb + OFF_OA + (lane >> 4) * 2048 + (32 * w + 2 * (lane & 15) + par) * 16;
#pragma unroll
  for (int j = 0; j < 5; j++) stsm4(oa + 4096 * j, ov + 4 * j);
  TSIF(par == 0 && w == 0, 120);
  fence_async_smem();
  TSIF(par == 0 && w == 0, 121);
  __syncwarp();
  if (lane == 0) mbar_arrive(sb + OFF_BAR + 8 * B_ATTN);
  TSM(w == 0 || w == 2, 122 + par + (w == 2 ? 3 : 0));
}

struct Maps {
  CUtensorMap x, wm, wt, k, v, y, wo, qm, qt, om, ot;
};

__device__ __forceinline__ void load_stage(uint32_t sb, int kb, int b, const Maps& m) {
  const uint32_t st = sb + (kb & 3) * STAGE_BYTES, bar = sb + OFF_BAR + 8 * (B_FULL1 + (kb & 3));
  const int r = b >> 3, hg = b & 7, slab = kb - KV_KB;
  const bool kv = slab >= 0 && slab < 5;
  const uint32_t kbar = sb + OFF_BAR + 8 * (B_KV + slab), dst = sb + OFF_KVS + slab * KVS_BYTES;
  mbar_expect_tx(bar, STAGE_BYTES);
  if (kv) mbar_expect_tx(kbar, KVS_BYTES);
  tma_3d(st, &m.x, 64 * kb, 64 * r, 0, bar);
  tma_3d(st + ST_W, &m.wm, 80 * hg + (tail_first(hg) ? 16 : 0), 64 * kb, 0, bar);
  tma_3d(st + ST_WT, &m.wt, 80 * hg + (tail_first(hg) ? 0 : 64), 64 * kb, 0, bar);
  if (kv) tma_3d(dst, &m.k, 0, 32 * (b >> 1) - 3, 2 * slab + (b & 1), kbar);
  if (kv) tma_3d(dst + KVS_V, &m.v, 0, 32 * (b >> 1), 2 * slab + (b & 1), kbar);
}

__global__ void __launch_bounds__(NTHR, 1) fused_kernel(const __grid_constant__ Maps m, const Params p) {
  extern __shared__ __align__(1024) uint8_t smem[];
  const uint32_t sb = (uint32_t)__cvta_generic_to_shared(smem);
  const uint32_t bars = sb + OFF_BAR;
  const int tid = threadIdx.x, lane = tid & 31;
  int b = blockIdx.x;
  b = (((b & 63) >> 3) * 2 + (b & 1)) * 8 + (((b < 64 ? 0x6521 : 0x7430) >> (4 * ((b >> 1) & 3))) & 7);
  const int r = b >> 3, hg = b & 7;

  if (tid == T_ISSUE) {
    TSM(true, 0);
    mbar_init(bars + 8 * B_F0, 1);
    fence_async_smem();
    mbar_expect_tx(bars + 8 * B_F0, ST_WT);
    tma_3d(sb, &m.x, 0, 64 * r, 0, bars + 8 * B_F0);
    tma_3d(sb + ST_W, &m.wm, 80 * hg + (tail_first(hg) ? 16 : 0), 0, 0, bars + 8 * B_F0);
#pragma unroll
    for (int i = 0; i < 4; i++) mbar_init(bars + 8 * (B_FULL1 + i), 1);
    fence_async_smem();
    mbar_expect_tx(bars + 8 * B_FULL1, STAGE_BYTES - ST_WT);
    tma_3d(sb + ST_WT, &m.wt, 80 * hg + (tail_first(hg) ? 0 : 64), 0, 0, bars + 8 * B_FULL1);
    load_stage(sb, 1, b, m);
  } else if (tid == T_INIT) {
#pragma unroll
    for (int i = 0; i < B_F0; i++) mbar_init(bars + 8 * i, i < B_GATE ? 8 : i < B_CVD ? 4 : i == B_CVD ? 20 : 1);
    fence_async_smem();
  }
  const int warp = __shfl_sync(0xffffffffu, tid >> 5, 0), wg = warp >> 2, w = warp & 3;
  __syncthreads();

  if (wg == 3) {
    asm volatile("setmaxnreg.dec.sync.aligned.u32 56;");
    if (w == 0) {
      if (lane == 0) {
#pragma unroll 1
        for (int kb = 2; kb < 10; kb++) {
          if (kb >= 4) mbar_wait(bars + 8 * (kb == 7 ? B_E3 : B_EMPTY1 + (kb & 3)), (kb >> 3) & 1);
          TSIF(kb >= 4, 44 + kb);
          load_stage(sb, kb, b, m);
          TSIF(kb == 3, 60);
          if (kb == TRIG_KB) mbar_arrive(bars + 8 * B_LAST);
        }
        mbar_wait(bars + 8 * B_WOP, 0);
        mbar_wait(bars + 8 * WL_TRIG, 0);
        mbar_wait(bars + 8 * B_EPOCH, 0);
        flag_wait(g_cnt + C_W + 32 * hg, (lds32(sb + OFF_EPOCH) + 1) * 16);
        TS(30);
#pragma unroll 1
        for (int j = 0; j < 8; j++) {
          if (j >= 6) mbar_wait(bars + 8 * (B_EMPTY2 + j - 6), 0);
          if (j == 4) mbar_wait(bars + 8 * B_ATTN, 0);
          TSIF(j >= 6, 100 + j);
          mbar_expect_tx(bars + 8 * (B_FULL2 + j), j == 0 ? WO_BYTES : j == 5 ? O_BYTES + WO_BYTES + 512 : O_BYTES + WO_BYTES);
          bulk_load(sb + off_w(j), g_WO + (hg * 8 + step_src(hg, j)) * 800, WO_BYTES, bars + 8 * (B_FULL2 + j));
        }
        mbar_wait(bars + 8 * (B_EMPTY2 + 3), 0);
        mbar_expect_tx(bars + 8 * B_QF, O_BYTES);
        tma_2d(sb + OFF_QS, &m.qm, 80 * hg, 128 * r, bars + 8 * B_QF);
        tma_2d(sb + OFF_QT, &m.qt, 80 * hg + 64, 128 * r, bars + 8 * B_QF);
      }
    } else if (w == 1) {
      unsigned epoch = 0;
      if (lane == 0) {
        epoch = atomicAdd(g_cnt + C_LAUNCH, 1u) / NCTA;
        asm volatile("st.shared.u32 [%0], %1;" ::"r"(sb + OFF_EPOCH), "r"(epoch) : "memory");
        mbar_arrive(bars + 8 * B_EPOCH);
        mbar_wait(bars + 8 * B_KVD, 0);
        mbar_expect_tx(bars + 8 * B_HB, 5 * 4096);
#pragma unroll 1
        for (int c = 0; c < 5; c++) {
          if (c == 3) mbar_wait(bars + 8 * B_S3, 0);
          bulk_load(sb + off_ch(c) + U_BYTES, p.ssm_k + (5 * b + c) * SEQ, 4096, bars + 8 * B_HB);
        }
#pragma unroll
        for (int c = 0; c < 4; c++) mbar_expect_tx(bars + 8 * (B_U + c), c < 3 ? U_BYTES : 2 * U_BYTES);
        const uint4* usrc = g_U + 5 * b * U_PITCH;
        mbar_wait(bars + 8 * B_USIG, 0);
        flag_wait(g_cnt + C_PREP + 32 * (b & 15), (epoch + 1) * NCTA);
        TS(23);
#pragma unroll
        for (int c = 0; c < 5; c++) {
          if (c == 3) mbar_wait(bars + 8 * (B_U + 2), 0);
          bulk_load(sb + off_ch(c), usrc + c * U_PITCH, U_BYTES, bars + 8 * (B_U + (c < 3 ? c : 3)));
          TSIF(c == 0 || c == 4, 116 + (c >> 2));
        }
      }
      epoch = __shfl_sync(0xffffffffu, epoch, 0);
      if (lane < 8) {
        const int src = (b & ~7) | step_src(hg, lane);
        mbar_wait(bars + 8 * B_ATTN, 0);
        TS(20);
        bool seen = false;
#pragma unroll 1
        for (int spins = 0; spins < SPIN_LIMIT; spins++) {
          const bool now = !seen && (int)(flag_read(g_cnt + C_O + 32 * src) - (epoch + 1)) >= 0;
          if (now && lane >= 1 && lane < 4) bulk_load(sb + off_o(lane), g_O + src * 1280, O_BYTES, bars + 8 * (B_FULL2 + lane));
          seen = seen || now;
          if (__all_sync(0xff, seen)) break;
        }
        TS(21);
        if (lane == 5) bulk_load(sb + OFF_GATE, g_gate + 128 * r, 512, bars + 8 * (B_FULL2 + 5));
#pragma unroll 1
        for (int j = 4; j < 8; j++) {
          if (lane == j) {
            mbar_wait(bars + 8 * (j < 6 ? B_C34 : B_EMPTY2 + j - 6), 0);
            bulk_load(sb + off_o(j), g_O + src * 1280, O_BYTES, bars + 8 * (B_FULL2 + j));
          }
          __syncwarp(0xff);
        }
        TS(22);
      }
    } else if (w == 2) {
      mbar_wait(bars + 8 * B_PREP, 0);
      flag_signal(g_cnt + C_PREP, 16, lane);
      TS(25);
      if (lane == 0) {
        mbar_arrive(bars + 8 * B_USIG);
        mbar_expect_tx(bars + 8 * B_ORB, O_BYTES + 64);
        mbar_wait(bars + 8 * B_GATE, 0);
        publish(g_gate + 16 * b, sb + OFF_GATE + 64 * hg, 64, bars + 8 * B_ORB);
        mbar_wait(bars + 8 * B_ATTN, 0);
        publish(g_O + b * 1280, sb + OFF_OA, O_BYTES, bars + 8 * B_ORB);
        TS(74);
        mbar_wait(bars + 8 * B_ORB, 0);
        flag_bump(g_cnt + C_O + 32 * b);
        TS(26);
        mbar_arrive(bars + 8 * B_OSIG);
      }
    } else {
      if (lane == 0) {
        uint4* dst = g_WO + (hg * 8 + (r >> 1)) * 800 + (r & 1) * 80;
        mbar_wait(bars + 8 * B_S3, 0);
        asm volatile("cp.async.bulk.prefetch.L2.global [%0], 6400;" ::"l"(p.wo + b * 3200) : "memory");
        mbar_wait(bars + 8 * B_P1, 0);
        mbar_wait(bars + 8 * WB_TRIG, 0);
        mbar_expect_tx(bars + 8 * B_WST, WO_BYTES / 2);
        tma_3d(sb + OFF_WA, &m.wo, 0, 40 * r, 5 * hg, bars + 8 * B_WST);
        mbar_wait(bars + 8 * B_WST, 0);
#pragma unroll 1
        for (int n = 0; n < 5; n++) bulk_store(dst + 160 * n, sb + OFF_WA + 1280 * n, 1280);
        bulk_wait_read();
        mbar_expect_tx(bars + 8 * B_WST, WO_BYTES / 2);
#pragma unroll 1
        for (int n = 0; n < 5; n++) bulk_load(sb + OFF_WA + 1280 * n, dst + 160 * n, 1280, bars + 8 * B_WST);
        mbar_wait(bars + 8 * B_WST, 1);
        flag_bump(g_cnt + C_W + 32 * hg);
        mbar_arrive(bars + 8 * B_WOP);
        TS(71);
        mbar_expect_tx(bars + 8 * B_C34, 3 * U_BYTES);
        mbar_expect_tx(bars + 8 * B_YRB, 2 * U_BYTES);
#pragma unroll 1
        for (int c = 0; c < 5; c++) {
          mbar_wait(bars + 8 * (B_YST + c), 0);
          publish(g_U + (5 * b + c) * U_PITCH, sb + off_ch(c), U_BYTES, bars + 8 * (c < 3 ? B_C34 : B_YRB));
        }
        TS(75);
        mbar_wait(bars + 8 * B_C34, 0);
        mbar_wait(bars + 8 * B_YRB, 0);
        flag_bump(g_cnt + C_Y + 32 * (b >> 4));
        TS(27);
        mbar_arrive(bars + 8 * B_YSIG);
        mbar_expect_tx(bars + 8 * B_YFULL, 20480);
        flag_wait(g_cnt + C_Y + 32 * hg, (lds32(sb + OFF_EPOCH) + 1) * 16);
        TS(24);
        tma_2d(sb + OFF_YT, &m.y, 128 * r, 80 * hg, bars + 8 * B_YFULL);
        tma_2d(sb + OFF_YT + 10240, &m.y, 128 * r + 64, 80 * hg, bars + 8 * B_YFULL);
      }
    }
  } else {
    asm volatile("setmaxnreg.inc.sync.aligned.u32 152;");
    if (wg < 2) {
      float acc[120];
#pragma unroll
      for (int i = 0; i < 120; i++) acc[i] = 0.f;
      const uint32_t da = desc_lo(sb + wg * 8192, 16), db = desc_lo(sb + ST_W, 8192), dc = desc_lo(sb + ST_WT, 2048);
      if (HALO_INIT && w == 3 && b < NCTA - 8) {
        uint4* ho = g_halo + (b * 2 + wg) * 224 + lane;
#pragma unroll
        for (int j = 0; j < 7; j++)
          asm volatile("st.relaxed.gpu.global.v4.u32 [%0], {%1, %1, %1, %1};" ::"l"(ho + 32 * j), "r"(0) : "memory");
      }
      mbar_wait(bars + 8 * B_F0, 0);
      TSIF(w == 0 && wg == 0, 1);
      wg_fence();
#pragma unroll
      for (int k = 0; k < 4; k++) WgSST<192>::mma<HI_SW128, HI_SW128>(acc, da + 2 * k, db + 128 * k, 1);
      wg_commit();
      mbar_wait(bars + 8 * B_FULL1, 0);
      wg_fence();
#pragma unroll
      for (int k = 0; k < 4; k++) WgSST<48>::mma<HI_SW128, HI_SW32>(acc + 96, da + 2 * k, dc + 32 * k, 1);
      wg_commit();
#pragma unroll 1
      for (int kb = 1; kb < 10; kb++) {
        mbar_wait(bars + 8 * (B_FULL1 + (kb & 3)), (kb >> 2) & 1);
        const uint32_t so = (kb & 3) * (STAGE_BYTES >> 4);
        wg_fence();
#pragma unroll
        for (int k = 0; k < 4; k++) {
          WgSST<192>::mma<HI_SW128, HI_SW128>(acc, da + so + 2 * k, db + so + 128 * k, 1);
          WgSST<48>::mma<HI_SW128, HI_SW32>(acc + 96, da + so + 2 * k, dc + so + 32 * k, 1);
        }
        wg_commit();
        wg_wait<1>();
        if (lane == 0) mbar_arrive(bars + 8 * (kb == 4 ? B_E3 : B_EMPTY1 + ((kb - 1) & 3)));
      }
      mbar_wait(bars + 8 * B_EPOCH, 0);
      const uint32_t tag = lds32(sb + OFF_EPOCH) + 1;
      mbar_wait(bars + 8 * B_S3, 0);
      wg_wait<0>();
      pin<120>(acc);
      if (lane == 0) mbar_arrive(bars + 8 * B_P1);
      TSM(w == 0, 3 + wg);
      attention(acc, sb, b, wg, w, lane, tag);
    } else {
      const int tw = tid & 127, chl = 64 * (b & 1) + 8 * w + (lane >> 2);
      uint4* up = g_U + chl * U_PITCH + ((4 * (b >> 1) + (lane & 3)) ^ ((b >> 2) & 1));
      uint2 sw[10];
      uint32_t dv = 0;
      if (lane < 5) dv = __ldg(reinterpret_cast<const unsigned short*>(p.ssm_D) + 5 * b + lane);
#pragma unroll
      for (int i = 0; i < 10; i++) sw[i] = ldg64(reinterpret_cast<const uint2*>(p.shift_k) + chl + 128 * (i >> 1) + 32 * (i & 1));
      uint32_t tab[12];
      uint32_t tt[2];
      fft_tables(tab, tw);
      fft_twiddles(tt, tw);
      uint4 res[10];
#pragma unroll
      for (int i = 0; i < 10; i++) res[i] = make_uint4(0, 0, 0, 0);
#pragma unroll 1
      for (int slab = 0; slab < 5; slab++) {
#pragma unroll
        for (int i = 0; i < 8; i++) res[i] = res[i + 2];
        prep_slab(res + 8, sw, sb, slab, w, lane);
        TSIF(w == 0, 99 + 4 * slab);
#pragma unroll
        for (int i = 0; i < 8; i++) sw[i] = sw[i + 2];
      }
      TSIF(w == 0, 28);
      __syncwarp();
      if (lane == 0) mbar_arrive(bars + 8 * B_KVD + ((res[8].x ^ res[9].x) & p.zero));
      mbar_wait(bars + 8 * B_KVD, 0);
      fft_tables_store(tab, sb, tw);
      mbar_wait(bars + 8 * B_LAST, 0);
#pragma unroll
      for (int i = 0; i < 10; i++) up[(128 * (i >> 1) + 32 * (i & 1)) * U_PITCH] = res[i];
      __syncwarp();
      if (lane == 0) mbar_arrive(bars + 8 * B_PREP);
      TSIF(w == 0, 5);
      mbar_wait(bars + 8 * B_LAST, 0);
      prep_gate(p, sb, b, w, lane);
      __syncwarp();
      if (lane == 0) mbar_arrive(bars + 8 * B_GATE);
      TSIF(w == 0, 72);
      mbar_wait(bars + 8 * B_HB, 0);
      TSIF(w == 0, 2);
      const uint32_t ha = sb + U_BYTES + ((tw >> 3) * 16 + 8 + (tw & 7)) * 16;
      uint4 hv[5];
#pragma unroll
      for (int c = 0; c < 5; c++) hv[c] = lds128(ha + off_ch(c));
      __syncwarp();
#pragma unroll
      for (int c = 0; c < 5; c++) sts128((ha ^ 16) + off_ch(c), hv[c].x, hv[c].y, hv[c].z, hv[c].w);
      asm volatile("st.shared.v2.u32 [%0], {%1, %2};" ::"r"(sb + OFF_TT + 8 * tw), "r"(tt[0]), "r"(tt[1]) : "memory");
      if (tw < 5) asm volatile("st.shared.f32 [%0], %1;" ::"r"(sb + OFF_D + 4 * tw), "f"(bf_lo(dv) * 0.125f) : "memory");
      fence_async_smem();
      __syncwarp();
      if (lane == 0) mbar_arrive(bars + 8 * B_HA);
      TSIF(w == 0, 6);
    }

    FftConst fc;
    TSM(w == 0 && wg == 0, 104);
    mbar_wait(bars + 8 * B_HA, 0);
    fft_matrices(fc, sb, w, lane);
    TSM(w == 0 && wg == 0, 105);
    TSM(w == 0 && wg == 2, 124);
#pragma unroll 1
    for (uint32_t tasks = wg == 0 ? TASK0 : wg == 1 ? TASK1 : TASK2; tasks; tasks >>= 4) {
      const int c = (tasks & 7) - 1;
      conv_channel(fc, sb, c, wg, w, lane);
      if (lane == 0) mbar_arrive(bars + 8 * (B_YST + c));
      TSM(w == 0, 10 + c);
    }

    if (wg < 2) {
      const int g = lane >> 2;
      float acc[40];
#pragma unroll
      for (int i = 0; i < 40; i++) acc[i] = 0.f;
      const uint32_t da = desc_lo(sb + wg * 1024, 2048), db = desc_lo(sb, 2560);
      mbar_wait(bars + 8 * B_ORB, 0);
      mbar_wait(bars + 8 * B_FULL2, 0);
      mbar_wait(bars + 8 * B_CVD, 0);
      TSM(w == 0, 15 + wg);
#pragma unroll 1
      for (int j = 0; j < 8; j++) {
        mbar_wait(bars + 8 * (B_FULL2 + j), 0);
        TSM(w == 0 && wg == 0, 44 + (j < 4 ? j : j + 6));
        const uint32_t oa = da + (off_o(j) >> 4), ob = db + (off_w(j) >> 4);
        wg_fence();
#pragma unroll
        for (int k = 0; k < 5; k++) WgSST<80>::mma<HI_NONE, HI_SW32>(acc, oa + 256 * k, ob + 32 * k, 1);
        wg_commit();
        wg_wait<1>();
        if (j >= 1 && j <= 4 && lane == 0) mbar_arrive(bars + 8 * (B_EMPTY2 + j - 1));
      }
      TSIF(w == 0 && wg == 0, 113);
      const int tr = 64 * wg + 16 * w + (lane & 15);
      const uint32_t fm = sb + OFF_QS + tr * 128, fx = (lane >> 4) ^ (tr & 7);
      const uint32_t ft = sb + OFF_QT + tr * 32 + (((lane >> 4) ^ (tr >> 2)) & 1) * 16;
      const float g0 = __uint_as_float(lds32(sb + OFF_GATE + (64 * wg + 16 * w + g) * 4));
      const float g1 = __uint_as_float(lds32(sb + OFF_GATE + (64 * wg + 16 * w + 8 + g) * 4));
      const uint32_t ga = pack2(g0, g0), gb = pack2(g1, g1);
      const uint32_t na = pack2(1.f - g0, 1.f - g0), nb = pack2(1.f - g1, 1.f - g1);

      uint32_t qf[20];
      mbar_wait(bars + 8 * B_QF, 0);
      TSM(w == 0 && wg == 0, 99);
#pragma unroll
      for (int j = 0; j < 5; j++) ldsm4(qf + 4 * j, j < 4 ? fm + ((fx ^ (2 * j)) << 4) : ft);
#pragma unroll
      for (int i = 0; i < 20; i++) {
        qf[i] = bmul((i & 1) ? gb : ga, qf[i]);
        asm volatile("" : "+r"(qf[i]));
      }

      wg_wait<0>();
      pin<40>(acc);
      TSM(w == 0, 17 + wg);
      uint32_t pb[20];
#pragma unroll
      for (int j = 0; j < 10; j++) {
        pb[2 * j] = bmul(na, pack2(acc[4 * j], acc[4 * j + 1]));
        pb[2 * j + 1] = bmul(nb, pack2(acc[4 * j + 2], acc[4 * j + 3]));
        asm volatile("" : "+r"(pb[2 * j]), "+r"(pb[2 * j + 1]));
      }
      const uint32_t ya = sb + OFF_YT + wg * 10240 + ((lane >> 4) * 8 + (lane & 7)) * 128 +
                          (((2 * w + (((lane >> 3) & 1) ^ wg)) ^ (lane & 7)) << 4);
      mbar_wait(bars + 8 * B_YFULL, 0);
      TSM(w == 0 && wg == 0, 19);
#pragma unroll
      for (int j = 0; j < 5; j++) {
        uint32_t y[4];
        ldsm4t(y, ya + 2048 * j);
#pragma unroll
        for (int i = 0; i < 4; i++)
          qf[4 * j + i] = bfma(qf[4 * j + i], y[i], pb[4 * j + i]);
      }
#pragma unroll
      for (int j = 0; j < 5; j++) stsm4(j < 4 ? fm + ((fx ^ (2 * j)) << 4) : ft, qf + 4 * j);
      fence_async_smem();
      __syncwarp();
      if (lane == 0) {
        const int row = 64 * wg + 16 * w;
        asm volatile("cp.async.bulk.tensor.2d.global.shared::cta.bulk_group [%0, {%2, %3}], [%1];"
                     ::"l"(&m.om), "r"(sb + OFF_QS + row * 128), "r"(80 * hg), "r"(128 * r + row) : "memory");
        asm volatile("cp.async.bulk.tensor.2d.global.shared::cta.bulk_group [%0, {%2, %3}], [%1];"
                     ::"l"(&m.ot), "r"(sb + OFF_QT + row * 32), "r"(80 * hg + 64), "r"(128 * r + row) : "memory");
        asm volatile("cp.async.bulk.commit_group;\ncp.async.bulk.wait_group.read 0;" ::: "memory");
      }
      TSM(w == 0 || w == 3, 40 + 2 * wg + (w & 1));
    }
  }
}

typedef CUresult (*EncodeFn)(CUtensorMap*, CUtensorMapDataType, cuuint32_t, void*, const cuuint64_t*, const cuuint64_t*,
                             const cuuint32_t*, const cuuint32_t*, CUtensorMapInterleave, CUtensorMapSwizzle,
                             CUtensorMapL2promotion, CUtensorMapFloatOOBfill);

void encode(EncodeFn fn, CUtensorMap* tm, const void* base, int rank, const cuuint64_t* dims, const cuuint64_t* strides,
            const cuuint32_t* box, CUtensorMapSwizzle swz) {
  const cuuint32_t ones[3] = {1, 1, 1};
  fn(tm, CU_TENSOR_MAP_DATA_TYPE_BFLOAT16, rank, const_cast<void*>(base), dims, strides, box, ones,
     CU_TENSOR_MAP_INTERLEAVE_NONE, swz, CU_TENSOR_MAP_L2_PROMOTION_L2_128B, CU_TENSOR_MAP_FLOAT_OOB_FILL_NONE);
}

}

extern "C" void kernel_launch(void* const* d_in, const int* in_sizes, int n_in, void* d_out, int out_size) {
  (void)in_sizes; (void)n_in; (void)out_size;
  Params p;
  p.q = (const __nv_bfloat16*)d_in[0];
  p.k = (const __nv_bfloat16*)d_in[1];
  p.v = (const __nv_bfloat16*)d_in[2];
  p.shift_k = (const __nv_bfloat16*)d_in[3];
  p.ssm_k = (const __nv_bfloat16*)d_in[4];
  p.ssm_D = (const __nv_bfloat16*)d_in[5];
  p.wqkv = (const __nv_bfloat16*)d_in[7];
  p.wo = (const __nv_bfloat16*)d_in[8];
  p.gate_w = (const __nv_bfloat16*)d_in[9];
  p.out = (__nv_bfloat16*)d_out;
  p.zero = 0;

  static EncodeFn fn = nullptr;
  static void* yaddr = nullptr;
  if (!fn) {
    cudaDriverEntryPointQueryResult qr;
    void* f = nullptr;
    cudaGetDriverEntryPoint("cuTensorMapEncodeTiled", &f, cudaEnableDefault, &qr);
    fn = (EncodeFn)f;
    cudaGetSymbolAddress(&yaddr, g_U);
    cudaFuncSetAttribute(fused_kernel, cudaFuncAttributeMaxDynamicSharedMemorySize, SMEM_BYTES);
  }
  Maps m;
  {
    const cuuint64_t dims[3] = {640, 1024, 2}, st[2] = {2560, 1280};
    const cuuint32_t box[3] = {64, 64, 2};
    encode(fn, &m.x, p.q, 3, dims, st, box, CU_TENSOR_MAP_SWIZZLE_128B);
  }
  {
    const cuuint64_t dims[3] = {640, 640, 3}, st[2] = {3840, 1280};
    const cuuint32_t box[3] = {64, 64, 3}, boxt[3] = {16, 64, 3};
    encode(fn, &m.wm, p.wqkv, 3, dims, st, box, CU_TENSOR_MAP_SWIZZLE_128B);
    encode(fn, &m.wt, p.wqkv, 3, dims, st, boxt, CU_TENSOR_MAP_SWIZZLE_32B);
  }
  {
    const cuuint64_t dims[3] = {64, 2048, 10}, st[2] = {1280, 128};
    const cuuint32_t boxk[3] = {64, 35, 1}, boxv[3] = {64, 32, 1};
    encode(fn, &m.k, p.k, 3, dims, st, boxk, CU_TENSOR_MAP_SWIZZLE_128B);
    encode(fn, &m.v, p.v, 3, dims, st, boxv, CU_TENSOR_MAP_SWIZZLE_128B);
  }
  {
    const cuuint64_t dims[3] = {16, 640, 40}, st[2] = {1280, 32};
    const cuuint32_t box[3] = {16, 40, 5};
    encode(fn, &m.wo, p.wo, 3, dims, st, box, CU_TENSOR_MAP_SWIZZLE_32B);
  }
  {
    const cuuint64_t dims[2] = {2048, 640}, st[1] = {U_PITCH * 16};
    const cuuint32_t box[2] = {64, 80};
    encode(fn, &m.y, yaddr, 2, dims, st, box, CU_TENSOR_MAP_SWIZZLE_128B);
  }
  {
    const cuuint64_t dims[2] = {640, 2048}, st[1] = {1280};
    const cuuint32_t bqm[2] = {64, 128}, bqt[2] = {16, 128}, bom[2] = {64, 16}, bot[2] = {16, 16};
    encode(fn, &m.qm, p.q, 2, dims, st, bqm, CU_TENSOR_MAP_SWIZZLE_128B);
    encode(fn, &m.qt, p.q, 2, dims, st, bqt, CU_TENSOR_MAP_SWIZZLE_32B);
    encode(fn, &m.om, p.out, 2, dims, st, bom, CU_TENSOR_MAP_SWIZZLE_128B);
    encode(fn, &m.ot, p.out, 2, dims, st, bot, CU_TENSOR_MAP_SWIZZLE_32B);
  }
  fused_kernel<<<NCTA, NTHR, SMEM_BYTES>>>(m, p);
}
```

```cpp
#include <cuda.h>
#include <cuda_bf16.h>
#include <cuda_runtime.h>
#include <stdint.h>

namespace {

constexpr int SEQ = 2048, DIM = 640, NCTA = 128, NTHR = 512;

#define TRIG_KB 9
#define KV_KB 2
#define DEV_EXIT 0
#define FENCE_LO 0
#define FENCE_HI 0
#define WB_TRIG B_USIG
#define T_ISSUE 256
#define Q_SWAP 2
#define T_INIT 448
#define TASK0 0x3
#define TASK1 0x52
#define TASK2 0x41
#define WL_TRIG B_WOP

constexpr uint32_t STAGE_BYTES = 47104, ST_W = 16384, ST_WT = 40960;
constexpr uint32_t O_BYTES = 20480, WO_BYTES = 12800;
constexpr uint32_t OFF_OA = 0;
constexpr uint32_t OFF_QS = Q_SWAP ? 163840 : 3 * O_BYTES, OFF_QT = OFF_QS + 16384;
constexpr uint32_t OFF_WC = 81920;
constexpr uint32_t OFF_WA = 94720;
constexpr uint32_t OFF_GATE = 145920;
constexpr uint32_t OFF_TT = 146432;
constexpr uint32_t OFF_KVX = 148480;
constexpr uint32_t OFF_CH3 = 163840;
constexpr uint32_t CH_BYTES = 12288, U_BYTES = 4096;
constexpr uint32_t OFF_FT = 225280, OFF_GT = 229376;
constexpr uint32_t OFF_CH0 = 188416;
constexpr uint32_t OFF_KVS = OFF_CH0, KVS_V = 4480, KVS_BYTES = 8576;
constexpr uint32_t OFF_YT = Q_SWAP ? Q_SWAP * O_BYTES : 163840;
constexpr uint32_t OFF_BAR = 231936;
constexpr uint32_t SMEM_BYTES = OFF_BAR + 512;

enum : uint32_t {
  B_EMPTY1 = 0, B_S3 = 3, B_E3 = 4, B_EMPTY2 = 5, B_ATTN = 9, B_P1 = 10,
  B_GATE = 11, B_HA = 12, B_KVD = 13, B_PREP = 14, B_YST = 15,
  B_CVD = 20,
  B_FULL2 = 21, B_U = 29, B_KV = 33, B_HB = 38, B_C34 = 39, B_YRB = 40, B_YFULL = 41, B_EPOCH = 42, B_LAST = 43, B_OSIG = 44,
  B_WOP = 45, B_USIG = 46, B_WST = 47, B_QF = 48, B_ORB = 49, B_YSIG = 50,
  B_F0 = 51, B_FULL1 = 52
};
constexpr uint32_t OFF_EPOCH = OFF_BAR + 8 * 58, OFF_D = OFF_BAR + 8 * 60;
__device__ __forceinline__ uint32_t off_o(int j) { return j < 4 ? OFF_OA + j * O_BYTES : j < 6 ? OFF_CH0 + (j - 4) * O_BYTES : OFF_OA + (j - 6) * O_BYTES; }
__device__ __forceinline__ uint32_t off_w(int j) { return j < 4 ? OFF_WA + j * WO_BYTES : j == 4 ? OFF_KVX : j == 5 ? OFF_WC : OFF_WA + (j - 6) * WO_BYTES; }
__device__ __forceinline__ int step_src(int hg, int j) { return j == 0 ? hg : j <= hg ? j - 1 : j; }
__device__ __forceinline__ bool tail_first(int hg) { return (hg & 3) == 3; }
__device__ __forceinline__ uint32_t off_ch(int c) { return (c < 3 ? OFF_CH0 : OFF_CH3 - 3 * CH_BYTES) + c * CH_BYTES; }

#define U_PITCH 264
__device__ __align__(1024) uint4 g_U[DIM * U_PITCH];
__device__ uint4 g_O[NCTA * 1280];
__device__ uint4 g_WO[64 * 800];
__device__ uint4 g_halo[NCTA * 2 * 7 * 32];
__device__ __align__(128) float g_gate[SEQ];
__device__ unsigned g_cnt[32 * (1 + 2 * 16 + 8 + NCTA)];
constexpr int C_LAUNCH = 0, C_PREP = 32, C_Y = 32 * 17, C_W = 32 * 33, C_O = 32 * 41;

#define TSM(cond, slot) do { } while (0)
#define TSIF(cond, slot) do { if (__LINE__ >= FENCE_LO && __LINE__ < FENCE_HI) sched_fence(); } while (0)
__device__ __forceinline__ void sched_fence() {
  asm volatile("{\n.reg .pred p;\n.reg .u32 c;\nmov.u32 c, %%clock;\nsetp.eq.u32 p, c, 0;\n@p st.shared.u32 [%0], c;\n}"
               ::"r"(1024 + OFF_EPOCH + 4) : "memory");
}
#define TS(slot) TSIF(true, slot)

struct Params {
  const __nv_bfloat16 *q, *k, *v, *shift_k, *ssm_k, *ssm_D, *wqkv, *wo, *gate_w;
  __nv_bfloat16* out;
  uint32_t zero;
};

constexpr int SPIN_LIMIT = 1 << 17;

__device__ __forceinline__ void mbar_init(uint32_t bar, uint32_t count) {
  asm volatile("mbarrier.init.shared::cta.b64 [%0], %1;" ::"r"(bar), "r"(count) : "memory");
}
__device__ __forceinline__ void mbar_expect_tx(uint32_t bar, uint32_t bytes) {
  asm volatile("mbarrier.arrive.expect_tx.shared::cta.b64 _, [%0], %1;" ::"r"(bar), "r"(bytes) : "memory");
}
__device__ __forceinline__ void mbar_arrive(uint32_t bar) {
  asm volatile("mbarrier.arrive.shared::cta.b64 _, [%0];" ::"r"(bar) : "memory");
}
__device__ __forceinline__ void mbar_wait(uint32_t bar, uint32_t parity) {
  uint32_t ok;
  int spins = 0;
  do {
      asm volatile("{\n.reg .pred p;\nmbarrier.try_wait.parity.shared::cta.b64 p, [%1], %2;\nselp.b32 %0, 1, 0, p;\n}"
                   : "=r"(ok) : "r"(bar), "r"(parity) : "memory");
    if (++spins > SPIN_LIMIT) break;
  } while (!ok);
}
__device__ __forceinline__ unsigned flag_read(const unsigned* p) {
  unsigned v;
  asm volatile("ld.relaxed.gpu.global.u32 %0, [%1];" : "=r"(v) : "l"(p) : "memory");
  return v;
}
__device__ __forceinline__ void flag_poll(const unsigned* p, unsigned target) {
  unsigned v;
  int spins = 0;
  do {
    asm volatile("ld.relaxed.gpu.global.u32 %0, [%1];" : "=r"(v) : "l"(p) : "memory");
    if (++spins > SPIN_LIMIT) break;
  } while ((int)(v - target) < 0);
}
__device__ __forceinline__ void flag_wait(const unsigned* p, unsigned target) {
  flag_poll(p, target);
}
__device__ __forceinline__ void flag_signal(unsigned* p, int n, int lane) {
  if (lane == 0) asm volatile("fence.release.gpu;" ::: "memory");
  __syncwarp();
  if (lane < n) asm volatile("red.relaxed.gpu.global.add.u32 [%0], 1;" ::"l"(p + 32 * lane) : "memory");
}
__device__ __forceinline__ void flag_bump(unsigned* p) {
  asm volatile("red.relaxed.gpu.global.add.u32 [%0], 1;" ::"l"(p) : "memory");
}
__device__ __forceinline__ void fence_async_smem() { asm volatile("fence.proxy.async.shared::cta;" ::: "memory"); }
__device__ __forceinline__ void wg_sync(int id) { asm volatile("bar.sync %0, 128;" ::"r"(id) : "memory"); }

__device__ __forceinline__ void tma_2d(uint32_t dst, const CUtensorMap* tm, int c0, int c1, uint32_t bar) {
  asm volatile("cp.async.bulk.tensor.2d.shared::cluster.global.mbarrier::complete_tx::bytes [%0], [%1, {%3, %4}], [%2];"
               ::"r"(dst), "l"(tm), "r"(bar), "r"(c0), "r"(c1) : "memory");
}
__device__ __forceinline__ void tma_3d(uint32_t dst, const CUtensorMap* tm, int c0, int c1, int c2, uint32_t bar) {
  asm volatile("cp.async.bulk.tensor.3d.shared::cluster.global.mbarrier::complete_tx::bytes [%0], [%1, {%3, %4, %5}], [%2];"
               ::"r"(dst), "l"(tm), "r"(bar), "r"(c0), "r"(c1), "r"(c2) : "memory");
}
__device__ __forceinline__ void bulk_load(uint32_t dst, const void* src, uint32_t bytes, uint32_t bar) {
  asm volatile("cp.async.bulk.shared::cluster.global.mbarrier::complete_tx::bytes [%0], [%1], %2, [%3];"
               ::"r"(dst), "l"(src), "r"(bytes), "r"(bar) : "memory");
}
__device__ __forceinline__ void bulk_store(void* dst, uint32_t src, uint32_t bytes) {
  asm volatile("cp.async.bulk.global.shared::cta.bulk_group [%0], [%1], %2;" ::"l"(dst), "r"(src), "r"(bytes) : "memory");
}
__device__ __forceinline__ void bulk_wait_read() {
  asm volatile("cp.async.bulk.commit_group;\ncp.async.bulk.wait_group.read 0;" ::: "memory");
}

__device__ __forceinline__ void publish(void* dst, uint32_t src, uint32_t bytes, uint32_t bar) {
  bulk_store(dst, src, bytes);
  bulk_wait_read();
  bulk_load(src, dst, bytes, bar);
}

__device__ __forceinline__ void wg_fence() { asm volatile("wgmma.fence.sync.aligned;" ::: "memory"); }
__device__ __forceinline__ void wg_commit() { asm volatile("wgmma.commit_group.sync.aligned;" ::: "memory"); }
template <int N> __device__ __forceinline__ void wg_wait() { asm volatile("wgmma.wait_group.sync.aligned %0;" ::"n"(N) : "memory"); }
__device__ __forceinline__ uint32_t desc_lo(uint32_t addr, uint32_t lbo) { return ((addr & 0x3FFFF) >> 4) | ((lbo >> 4) << 16); }
constexpr uint32_t desc_hi(uint32_t sbo, uint32_t swz) { return (sbo >> 4) | (swz << 30); }
constexpr uint32_t HI_SW128 = desc_hi(1024, 1), HI_SW64 = desc_hi(512, 2), HI_SW32 = desc_hi(256, 3), HI_NONE = desc_hi(128, 0);
template <int N> __device__ __forceinline__ void pin(float* d) {
#pragma unroll
  for (int i = 0; i < N; i++) asm volatile("" : "+f"(d[i])::"memory");
}

__device__ __forceinline__ uint32_t lds32(uint32_t a) {
  uint32_t v;
  asm volatile("ld.volatile.shared.u32 %0, [%1];" : "=r"(v) : "r"(a) : "memory");
  return v;
}
__device__ __forceinline__ uint2 ldg64(const void* a) {
  uint2 v;
  asm volatile("ld.global.nc.v2.u32 {%0, %1}, [%2];" : "=r"(v.x), "=r"(v.y) : "l"(a) : "memory");
  return v;
}
__device__ __forceinline__ void ldsm4(uint32_t* r, uint32_t a) {
  asm volatile("ldmatrix.sync.aligned.m8n8.x4.shared.b16 {%0, %1, %2, %3}, [%4];"
               : "=r"(r[0]), "=r"(r[1]), "=r"(r[2]), "=r"(r[3]) : "r"(a) : "memory");
}
__device__ __forceinline__ void ldsm4t(uint32_t* r, uint32_t a) {
  asm volatile("ldmatrix.sync.aligned.m8n8.x4.trans.shared.b16 {%0, %1, %2, %3}, [%4];"
               : "=r"(r[0]), "=r"(r[1]), "=r"(r[2]), "=r"(r[3]) : "r"(a) : "memory");
}
__device__ __forceinline__ uint2 lds64(uint32_t a) {
  uint2 v;
  asm volatile("ld.shared.v2.u32 {%0, %1}, [%2];" : "=r"(v.x), "=r"(v.y) : "r"(a) : "memory");
  return v;
}
__device__ __forceinline__ uint4 lds128(uint32_t a) {
  uint4 v;
  asm volatile("ld.shared.v4.u32 {%0, %1, %2, %3}, [%4];" : "=r"(v.x), "=r"(v.y), "=r"(v.z), "=r"(v.w) : "r"(a) : "memory");
  return v;
}
__device__ __forceinline__ void sts128(uint32_t a, uint32_t x, uint32_t y, uint32_t z, uint32_t w) {
  asm volatile("st.shared.v4.u32 [%0], {%1, %2, %3, %4};" ::"r"(a), "r"(x), "r"(y), "r"(z), "r"(w) : "memory");
}
__device__ __forceinline__ void stsm4(uint32_t a, const uint32_t* r) {
  asm volatile("stmatrix.sync.aligned.m8n8.x4.shared.b16 [%0], {%1, %2, %3, %4};" ::"r"(a), "r"(r[0]), "r"(r[1]), "r"(r[2]), "r"(r[3]) : "memory");
}
__device__ __forceinline__ uint32_t pack2(float lo, float hi) {
  uint32_t r;
  asm("cvt.rn.bf16x2.f32 %0, %1, %2;" : "=r"(r) : "f"(hi), "f"(lo));
  return r;
}
__device__ __forceinline__ uint32_t movm(uint32_t a) {
  uint32_t d;
  asm volatile("movmatrix.sync.aligned.m8n8.trans.b16 %0, %1;" : "=r"(d) : "r"(a));
  return d;
}
__device__ __forceinline__ uint32_t bmul(uint32_t a, uint32_t b) {
  uint32_t d;
  asm("mul.rn.bf16x2 %0, %1, %2;" : "=r"(d) : "r"(a), "r"(b));
  return d;
}
__device__ __forceinline__ uint32_t badd(uint32_t a, uint32_t b) {
  uint32_t d;
  asm("add.rn.bf16x2 %0, %1, %2;" : "=r"(d) : "r"(a), "r"(b));
  return d;
}
__device__ __forceinline__ uint32_t bfma(uint32_t a, uint32_t b, uint32_t c) {
  uint32_t d;
  asm("fma.rn.bf16x2 %0, %1, %2, %3;" : "=r"(d) : "r"(a), "r"(b), "r"(c));
  return d;
}
__device__ __forceinline__ float bf_lo(uint32_t x) { return __uint_as_float(x << 16); }
__device__ __forceinline__ float bf_hi(uint32_t x) { return __uint_as_float(x & 0xFFFF0000u); }
__device__ __forceinline__ float ex2(float x) {
  float y;
  asm("ex2.approx.ftz.f32 %0, %1;" : "=f"(y) : "f"(x));
  return y;
}
__device__ __forceinline__ float rcp(float x) {
  float y;
  asm("rcp.approx.ftz.f32 %0, %1;" : "=f"(y) : "f"(x));
  return y;
}
__device__ __forceinline__ void mma16816(float* d, uint32_t a0, uint32_t a1, uint32_t a2, uint32_t a3, uint32_t b0, uint32_t b1) {
  asm volatile("mma.sync.aligned.m16n8k16.row.col.f32.bf16.bf16.f32 {%0, %1, %2, %3}, {%4, %5, %6, %7}, {%8, %9}, {%0, %1, %2, %3};"
               : "+f"(d[0]), "+f"(d[1]), "+f"(d[2]), "+f"(d[3])
               : "r"(a0), "r"(a1), "r"(a2), "r"(a3), "r"(b0), "r"(b1));
}
__device__ __forceinline__ void mma1688(float* d, uint32_t a0, uint32_t a1, uint32_t b0) {
  asm volatile("mma.sync.aligned.m16n8k8.row.col.f32.bf16.bf16.f32 {%0, %1, %2, %3}, {%4, %5}, {%6}, {%0, %1, %2, %3};"
               : "+f"(d[0]), "+f"(d[1]), "+f"(d[2]), "+f"(d[3])
               : "r"(a0), "r"(a1), "r"(b0));
}

template <int N> struct WgRS;
template <int N> struct WgSST;
template <> struct WgRS<32> {
  template <uint32_t HB>
  static __device__ __forceinline__ void mma(float* d, const uint32_t* a, uint32_t db) {
    asm volatile("{\n.reg .pred p;\n.reg .b64 db;\nsetp.ne.b32 p, %22, 0;\n"
      "mov.b64 db, {%20, %21};\n"
      "wgmma.mma_async.sync.aligned.m64n32k16.f32.bf16.bf16 {"
      "%0, %1, %2, %3, %4, %5, %6, %7, %8, %9, %10, %11, %12, %13, %14, %15"
      "}, {%16, %17, %18, %19}, db, p, 1, 1, 1;\n}\n"
      : "+f"(d[0]), "+f"(d[1]), "+f"(d[2]), "+f"(d[3]), "+f"(d[4]), "+f"(d[5]), "+f"(d[6]), "+f"(d[7]),
        "+f"(d[8]), "+f"(d[9]), "+f"(d[10]), "+f"(d[11]), "+f"(d[12]), "+f"(d[13]), "+f"(d[14]), "+f"(d[15])
      : "r"(a[0]), "r"(a[1]), "r"(a[2]), "r"(a[3]), "r"(db), "n"(HB), "n"(1));
  }
  template <uint32_t HB>
  static __device__ __forceinline__ void set(float* d, const uint32_t* a, uint32_t db) {
    asm volatile("{\n.reg .pred p;\n.reg .b64 db;\nsetp.ne.b32 p, %22, 0;\n"
      "mov.b64 db, {%20, %21};\n"
      "wgmma.mma_async.sync.aligned.m64n32k16.f32.bf16.bf16 {"
      "%0, %1, %2, %3, %4, %5, %6, %7, %8, %9, %10, %11, %12, %13, %14, %15"
      "}, {%16, %17, %18, %19}, db, p, 1, 1, 1;\n}\n"
      : "=f"(d[0]), "=f"(d[1]), "=f"(d[2]), "=f"(d[3]), "=f"(d[4]), "=f"(d[5]), "=f"(d[6]), "=f"(d[7]),
        "=f"(d[8]), "=f"(d[9]), "=f"(d[10]), "=f"(d[11]), "=f"(d[12]), "=f"(d[13]), "=f"(d[14]), "=f"(d[15])
      : "r"(a[0]), "r"(a[1]), "r"(a[2]), "r"(a[3]), "r"(db), "n"(HB), "n"(0));
  }
};
template <> struct WgRS<64> {
  template <uint32_t HB>
  static __device__ __forceinline__ void mma(float* d, const uint32_t* a, uint32_t db) {
    asm volatile("{\n.reg .pred p;\n.reg .b64 db;\nsetp.ne.b32 p, %38, 0;\n"
      "mov.b64 db, {%36, %37};\n"
      "wgmma.mma_async.sync.aligned.m64n64k16.f32.bf16.bf16 {"
      "%0, %1, %2, %3, %4, %5, %6, %7, %8, %9, %10, %11, %12, %13, %14, %15, "
      "%16, %17, %18, %19, %20, %21, %22, %23, %24, %25, %26, %27, %28, %29, %30, %31"
      "}, {%32, %33, %34, %35}, db, p, 1, 1, 1;\n}\n"
      : "+f"(d[0]), "+f"(d[1]), "+f"(d[2]), "+f"(d[3]), "+f"(d[4]), "+f"(d[5]), "+f"(d[6]), "+f"(d[7]),
        "+f"(d[8]), "+f"(d[9]), "+f"(d[10]), "+f"(d[11]), "+f"(d[12]), "+f"(d[13]), "+f"(d[14]), "+f"(d[15]),
        "+f"(d[16]), "+f"(d[17]), "+f"(d[18]), "+f"(d[19]), "+f"(d[20]), "+f"(d[21]), "+f"(d[22]), "+f"(d[23]),
        "+f"(d[24]), "+f"(d[25]), "+f"(d[26]), "+f"(d[27]), "+f"(d[28]), "+f"(d[29]), "+f"(d[30]), "+f"(d[31])
      : "r"(a[0]), "r"(a[1]), "r"(a[2]), "r"(a[3]), "r"(db), "n"(HB), "n"(1));
  }
  template <uint32_t HB>
  static __device__ __forceinline__ void set(float* d, const uint32_t* a, uint32_t db) {
    asm volatile("{\n.reg .pred p;\n.reg .b64 db;\nsetp.ne.b32 p, %38, 0;\n"
      "mov.b64 db, {%36, %37};\n"
      "wgmma.mma_async.sync.aligned.m64n64k16.f32.bf16.bf16 {"
      "%0, %1, %2, %3, %4, %5, %6, %7, %8, %9, %10, %11, %12, %13, %14, %15, "
      "%16, %17, %18, %19, %20, %21, %22, %23, %24, %25, %26, %27, %28, %29, %30, %31"
      "}, {%32, %33, %34, %35}, db, p, 1, 1, 1;\n}\n"
      : "=f"(d[0]), "=f"(d[1]), "=f"(d[2]), "=f"(d[3]), "=f"(d[4]), "=f"(d[5]), "=f"(d[6]), "=f"(d[7]),
        "=f"(d[8]), "=f"(d[9]), "=f"(d[10]), "=f"(d[11]), "=f"(d[12]), "=f"(d[13]), "=f"(d[14]), "=f"(d[15]),
        "=f"(d[16]), "=f"(d[17]), "=f"(d[18]), "=f"(d[19]), "=f"(d[20]), "=f"(d[21]), "=f"(d[22]), "=f"(d[23]),
        "=f"(d[24]), "=f"(d[25]), "=f"(d[26]), "=f"(d[27]), "=f"(d[28]), "=f"(d[29]), "=f"(d[30]), "=f"(d[31])
      : "r"(a[0]), "r"(a[1]), "r"(a[2]), "r"(a[3]), "r"(db), "n"(HB), "n"(0));
  }
};
template <> struct WgSST<48> {
  template <uint32_t HA, uint32_t HB>
  static __device__ __forceinline__ void mma(float* d, uint32_t da, uint32_t db, int sc) {
    asm volatile("{\n.reg .pred p;\n.reg .b64 da, db;\nsetp.ne.b32 p, %28, 0;\n"
      "mov.b64 da, {%24, %25};\nmov.b64 db, {%26, %27};\n"
      "wgmma.mma_async.sync.aligned.m64n48k16.f32.bf16.bf16 {"
      "%0, %1, %2, %3, %4, %5, %6, %7, %8, %9, %10, %11, %12, %13, %14, %15, "
      "%16, %17, %18, %19, %20, %21, %22, %23"
      "}, da, db, p, 1, 1, 0, 1;\n}\n"
      : "+f"(d[0]), "+f"(d[1]), "+f"(d[2]), "+f"(d[3]), "+f"(d[4]), "+f"(d[5]), "+f"(d[6]), "+f"(d[7]),
        "+f"(d[8]), "+f"(d[9]), "+f"(d[10]), "+f"(d[11]), "+f"(d[12]), "+f"(d[13]), "+f"(d[14]), "+f"(d[15]),
        "+f"(d[16]), "+f"(d[17]), "+f"(d[18]), "+f"(d[19]), "+f"(d[20]), "+f"(d[21]), "+f"(d[22]), "+f"(d[23])
      : "r"(da), "n"(HA), "r"(db), "n"(HB), "r"(sc));
  }
};
template <> struct WgSST<80> {
  template <uint32_t HA, uint32_t HB>
  static __device__ __forceinline__ void mma(float* d, uint32_t da, uint32_t db, int sc) {
    asm volatile("{\n.reg .pred p;\n.reg .b64 da, db;\nsetp.ne.b32 p, %44, 0;\n"
      "mov.b64 da, {%40, %41};\nmov.b64 db, {%42, %43};\n"
      "wgmma.mma_async.sync.aligned.m64n80k16.f32.bf16.bf16 {"
      "%0, %1, %2, %3, %4, %5, %6, %7, %8, %9, %10, %11, %12, %13, %14, %15, "
      "%16, %17, %18, %19, %20, %21, %22, %23, %24, %25, %26, %27, %28, %29, %30, %31, "
      "%32, %33, %34, %35, %36, %37, %38, %39"
      "}, da, db, p, 1, 1, 0, 1;\n}\n"
      : "+f"(d[0]), "+f"(d[1]), "+f"(d[2]), "+f"(d[3]), "+f"(d[4]), "+f"(d[5]), "+f"(d[6]), "+f"(d[7]),
        "+f"(d[8]), "+f"(d[9]), "+f"(d[10]), "+f"(d[11]), "+f"(d[12]), "+f"(d[13]), "+f"(d[14]), "+f"(d[15]),
        "+f"(d[16]), "+f"(d[17]), "+f"(d[18]), "+f"(d[19]), "+f"(d[20]), "+f"(d[21]), "+f"(d[22]), "+f"(d[23]),
        "+f"(d[24]), "+f"(d[25]), "+f"(d[26]), "+f"(d[27]), "+f"(d[28]), "+f"(d[29]), "+f"(d[30]), "+f"(d[31]),
        "+f"(d[32]), "+f"(d[33]), "+f"(d[34]), "+f"(d[35]), "+f"(d[36]), "+f"(d[37]), "+f"(d[38]), "+f"(d[39])
      : "r"(da), "n"(HA), "r"(db), "n"(HB), "r"(sc));
  }
};
template <> struct WgSST<192> {
  template <uint32_t HA, uint32_t HB>
  static __device__ __forceinline__ void mma(float* d, uint32_t da, uint32_t db, int sc) {
    asm volatile("{\n.reg .pred p;\n.reg .b64 da, db;\nsetp.ne.b32 p, %100, 0;\n"
      "mov.b64 da, {%96, %97};\nmov.b64 db, {%98, %99};\n"
      "wgmma.mma_async.sync.aligned.m64n192k16.f32.bf16.bf16 {"
      "%0, %1, %2, %3, %4, %5, %6, %7, %8, %9, %10, %11, %12, %13, %14, %15, "
      "%16, %17, %18, %19, %20, %21, %22, %23, %24, %25, %26, %27, %28, %29, %30, %31, "
      "%32, %33, %34, %35, %36, %37, %38, %39, %40, %41, %42, %43, %44, %45, %46, %47, "
      "%48, %49, %50, %51, %52, %53, %54, %55, %56, %57, %58, %59, %60, %61, %62, %63, "
      "%64, %65, %66, %67, %68, %69, %70, %71, %72, %73, %74, %75, %76, %77, %78, %79, "
      "%80, %81, %82, %83, %84, %85, %86, %87, %88, %89, %90, %91, %92, %93, %94, %95"
      "}, da, db, p, 1, 1, 0, 1;\n}\n"
      : "+f"(d[0]), "+f"(d[1]), "+f"(d[2]), "+f"(d[3]), "+f"(d[4]), "+f"(d[5]), "+f"(d[6]), "+f"(d[7]),
        "+f"(d[8]), "+f"(d[9]), "+f"(d[10]), "+f"(d[11]), "+f"(d[12]), "+f"(d[13]), "+f"(d[14]), "+f"(d[15]),
        "+f"(d[16]), "+f"(d[17]), "+f"(d[18]), "+f"(d[19]), "+f"(d[20]), "+f"(d[21]), "+f"(d[22]), "+f"(d[23]),
        "+f"(d[24]), "+f"(d[25]), "+f"(d[26]), "+f"(d[27]), "+f"(d[28]), "+f"(d[29]), "+f"(d[30]), "+f"(d[31]),
        "+f"(d[32]), "+f"(d[33]), "+f"(d[34]), "+f"(d[35]), "+f"(d[36]), "+f"(d[37]), "+f"(d[38]), "+f"(d[39]),
        "+f"(d[40]), "+f"(d[41]), "+f"(d[42]), "+f"(d[43]), "+f"(d[44]), "+f"(d[45]), "+f"(d[46]), "+f"(d[47]),
        "+f"(d[48]), "+f"(d[49]), "+f"(d[50]), "+f"(d[51]), "+f"(d[52]), "+f"(d[53]), "+f"(d[54]), "+f"(d[55]),
        "+f"(d[56]), "+f"(d[57]), "+f"(d[58]), "+f"(d[59]), "+f"(d[60]), "+f"(d[61]), "+f"(d[62]), "+f"(d[63]),
        "+f"(d[64]), "+f"(d[65]), "+f"(d[66]), "+f"(d[67]), "+f"(d[68]), "+f"(d[69]), "+f"(d[70]), "+f"(d[71]),
        "+f"(d[72]), "+f"(d[73]), "+f"(d[74]), "+f"(d[75]), "+f"(d[76]), "+f"(d[77]), "+f"(d[78]), "+f"(d[79]),
        "+f"(d[80]), "+f"(d[81]), "+f"(d[82]), "+f"(d[83]), "+f"(d[84]), "+f"(d[85]), "+f"(d[86]), "+f"(d[87]),
        "+f"(d[88]), "+f"(d[89]), "+f"(d[90]), "+f"(d[91]), "+f"(d[92]), "+f"(d[93]), "+f"(d[94]), "+f"(d[95])
      : "r"(da), "n"(HA), "r"(db), "n"(HB), "r"(sc));
  }
};

struct FftConst {
  uint32_t f[2][4], fi[4][4];
  uint32_t ta[2][2], tb[2][2];
};
__device__ __forceinline__ void cis(int m, float scale, float& c, float& s) {
  const float a = (float)m * (-6.283185307179586f * scale);
  c = __cosf(a);
  s = __sinf(a);
}
__device__ __forceinline__ void fft_tables(uint32_t (&v)[12], int tw) {
  const int row = tw >> 2, ch = tw & 3;
#pragma unroll
  for (int i = 0; i < 4; i++) {
    float c[2], s[2], x[2];
#pragma unroll
    for (int e = 0; e < 2; e++) {
      cis((((32 * (8 * ch + 2 * i + e) + 15) * (4 * row - 63) + 2048) & 4095) - 2048, 1.f / 4096, c[e], s[e]);
      float gc, gs;
      cis((((row & 15) * (8 * (ch & 1) + 2 * i + e) + 8) & 15) - 8, 1.f / 16, gc, gs);
      x[e] = (row >> 4) == (ch >> 1) ? gc : (ch >> 1) ? gs : -gs;
    }
    v[i] = pack2(c[0] * 0.125f, c[1] * 0.125f);
    v[4 + i] = pack2(s[0] * 0.125f, s[1] * 0.125f);
    v[8 + i] = pack2(x[0], x[1]);
  }
#pragma unroll
  for (int i = 0; i < 12; i++) asm volatile("" : "+r"(v[i]));
}
__device__ __forceinline__ void fft_tables_store(const uint32_t (&v)[12], uint32_t sb, int tw) {
  const int row = tw >> 2;
  const uint32_t x = ((tw ^ (row >> 1)) & 3) << 4, a = sb + OFF_FT + (16 * (row >> 3) + (row & 7)) * 64 + x;
  sts128(a, v[0], v[1], v[2], v[3]);
  sts128(a + 512, v[4], v[5], v[6], v[7]);
  sts128(sb + OFF_GT + row * 64 + x, v[8], v[9], v[10], v[11]);
}
__device__ __forceinline__ void fft_twiddles(uint32_t (&v)[2], int tw) {
  float a[2], s[2];
#pragma unroll
  for (int i = 0; i < 2; i++) {
    float c;
    cis((2 * (2 * (tw & 3) + i) - 15) * (4 * (tw >> 2) - 63), 1.f / 4096, c, s[i]);
    a[i] = __fdividef(-s[i], 1.f + c);
  }
  v[0] = pack2(a[0], a[1]);
  v[1] = pack2(s[0], s[1]);
  asm volatile("" : "+r"(v[0]), "+r"(v[1]));
}
__device__ __forceinline__ void fft_matrices(FftConst& k, uint32_t sb, int w, int lane) {
  const uint32_t x = (lane >> 1) & 3;
  const uint2 t0 = lds64(sb + OFF_TT + 256 * w + 8 * lane), t1 = lds64(sb + OFF_TT + 256 * w + 8 * (lane ^ 3));
  k.ta[0][0] = t0.x;
  k.tb[0][0] = t0.y;
  k.ta[1][1] = __byte_perm(t1.x, 0, 0x1032);
  k.tb[1][1] = __byte_perm(t1.y, 0, 0x1032);
#pragma unroll
  for (int j = 0; j < 2; j++) {
    k.ta[1 - j][j] = k.ta[j][j] ^ 0x80008000u;
    k.tb[1 - j][j] = k.tb[j][j] ^ 0x80008000u;
    asm volatile("" : "+r"(k.ta[0][j]), "+r"(k.tb[0][j]), "+r"(k.ta[1][j]), "+r"(k.tb[1][j]));
  }
#pragma unroll
  for (int i = 0; i < 2; i++) {
    ldsm4(k.f[i], sb + OFF_FT + (16 * w + (lane & 15)) * 64 + (((2 * i + (lane >> 4)) ^ x) << 4));
    ldsm4t(k.fi[i], sb + OFF_FT + (32 * i + lane) * 64 + ((w ^ x) << 4));
#pragma unroll
    for (int j = 0; j < 4; j++) {
      k.fi[2 + i][j] = (j & 1) ? k.fi[i][j - 1] ^ 0x80008000u : k.fi[i][j + 1];
      asm volatile("" : "+r"(k.fi[2 + i][j]));
    }
  }
}
__device__ __forceinline__ void rot(uint32_t& x, uint32_t& y, uint32_t a, uint32_t b) {
  x = bfma(a, y, x);
  y = bfma(b, x, y);
  x = bfma(a, y, x);
}
__device__ __forceinline__ void twiddle_fwd(uint32_t (&a)[4][4], float* d, const FftConst& k) {
#pragma unroll
  for (int q = 0; q < 4; q++)
#pragma unroll
    for (int j = 0; j < 2; j++) {
      const float* x = d + 8 * q + 4 * j;
      uint32_t re = pack2(x[0], x[1]), im = pack2(x[2], x[3]);
      rot(re, im, k.ta[0][j], k.tb[0][j]);
      a[q & 2][2 * j + (q & 1)] = re;
      a[(q & 2) + 1][2 * j + (q & 1)] = im;
    }
}
__device__ __forceinline__ void g_step(float* d, const uint32_t (&a)[4][4], uint32_t dre, uint32_t dim) {
  WgRS<32>::set<HI_SW64>(d, a[0], dre);
  WgRS<32>::set<HI_SW64>(d + 16, a[2], dre);
  WgRS<32>::mma<HI_SW64>(d, a[1], dim);
  WgRS<32>::mma<HI_SW64>(d + 16, a[3], dim);
  wg_commit();
}

__device__ __forceinline__ void products(uint32_t (&a)[4][4], const float* H, const float* U, int p) {
#pragma unroll
  for (int j = 0; j < 2; j++)
#pragma unroll
    for (int m = 2 * p; m < 2 * p + 2; m++) {
      float pr[2], pi[2];
#pragma unroll
      for (int x = 0; x < 2; x++)
#pragma unroll
        for (int q = 0; q <= m; q++) {
          const int ih = 16 * (q >> 1) + 2 * (q & 1) + 4 * j + x, iu = 16 * ((m - q) >> 1) + 2 * ((m - q) & 1) + 4 * j + x;
          pr[x] = q ? fmaf(H[ih], U[iu], pr[x]) : H[ih] * U[iu];
          pi[x] = q ? fmaf(H[ih], U[iu + 8], pi[x]) : H[ih] * U[iu + 8];
          pr[x] = fmaf(-H[ih + 8], U[iu + 8], pr[x]);
          pi[x] = fmaf(H[ih + 8], U[iu], pi[x]);
        }
      a[m & 2][2 * j + (m & 1)] = pack2(pr[0], pr[1]);
      a[(m & 2) + 1][2 * j + (m & 1)] = pack2(pi[0], pi[1]);
    }
}

__device__ __forceinline__ void conv_channel(const FftConst& k, uint32_t sb, int c, int wg, int w, int lane) {
  const uint32_t cb = sb + off_ch(c), bars = sb + OFF_BAR;
  const uint32_t du = desc_lo(cb, 1024), dg = desc_lo(sb + OFF_GT, 16), dz = desc_lo(cb + U_BYTES, 16);
  float U[32], H[32];
  uint32_t a[4][4], e[4][4];
  const float dv = __uint_as_float(lds32(sb + OFF_D + 4 * c));
  wg_fence();
  WgRS<64>::set<HI_SW32>(H, k.f[0], du + 256);
  WgRS<64>::mma<HI_SW32>(H, k.f[1], du + 256 + 32);
  wg_commit();
  wg_wait<0>();
  pin<32>(H);
  twiddle_fwd(a, H, k);
  mbar_wait(bars + 8 * (B_U + (c < 3 ? c : 3)), 0);
  TSM(w == 0 && c < 3, 7 + wg);
  wg_fence();
  WgRS<64>::set<HI_SW32>(U, k.f[0], du);
  WgRS<64>::mma<HI_SW32>(U, k.f[1], du + 32);
  wg_commit();
  g_step(H, a, dg, dg + 64);
  wg_wait<1>();
  pin<32>(U);
  twiddle_fwd(e, U, k);
  wg_fence();
  g_step(U, e, dg, dg + 64);
  wg_wait<0>();
  pin<32>(U);
  pin<32>(H);
#pragma unroll
  for (int j = 0; j < 4; j++) H[4 * (j >> 1) + (j & 1)] += dv;
  float V[32];
#pragma unroll
  for (int p = 0; p < 2; p++) {
    products(a, H, U, p);
    wg_fence();
    WgRS<32>::set<HI_SW64>(V + 16 * p, a[2 * p], dg + 64);
    WgRS<32>::mma<HI_SW64>(V + 16 * p, a[2 * p + 1], dg);
    wg_commit();
  }
  const uint32_t za = cb + U_BYTES + (8 * w + (lane & 7)) * 128 + (((lane >> 3) ^ (lane & 7)) << 4);
  const uint32_t ya = cb + (lane >> 4) * 1024 + (8 * w + (lane & 7)) * 32 + ((((lane >> 3) ^ (lane >> 2)) & 1) << 4);
  wg_sync(1 + wg);
#pragma unroll
  for (int p = 0; p < 2; p++) {
    if (p == 0) wg_wait<1>();
    else wg_wait<0>();
    pin<16>(V + 16 * p);
#pragma unroll
    for (int i = 0; i < 4; i++) {
      const int j = i & 1;
      const float* x = V + 16 * p + 4 * j + (i & 2);
      e[p][i] = pack2(x[8], x[9]);
      e[2 + p][i] = pack2(x[0], x[1]);
      rot(e[p][i], e[2 + p][i], k.ta[1][j], k.tb[1][j]);
    }
    stsm4(za ^ (64 * p), e[p]);
    stsm4((za ^ (64 * p)) + 4096, e[2 + p]);
  }
  fence_async_smem();
  wg_sync(1 + wg);
  wg_fence();
  WgRS<64>::set<HI_SW128>(H, k.fi[0], dz);
#pragma unroll
  for (int ks = 1; ks < 4; ks++) WgRS<64>::mma<HI_SW128>(H, k.fi[ks], dz + 128 * ks);
  wg_commit();
  wg_wait<0>();
  pin<32>(H);
  if (lane == 0) mbar_arrive(bars + 8 * B_CVD);
  TSIF(w == 0, 88 + c);
#pragma unroll
  for (int j = 0; j < 8; j++)
    a[j >> 2][j & 3] = j < 2 ? pack2(H[4 * j], H[4 * j + 1]) : pack2(H[4 * j] + H[4 * j - 6], H[4 * j + 1] + H[4 * j - 5]);
  stsm4(ya, a[0]);
  stsm4(ya + 2048, a[1]);
  fence_async_smem();
  __syncwarp();
}

__device__ __forceinline__ void prep_slab(uint4* res, const uint2* sw, uint32_t sb, int slab, int w, int lane) {
  const int t = lane & 3, tp = (lane & 7) >> 1, pos = 8 * tp + 2 * (((lane >> 3) + tp) & 3) + (lane & 1);
  const uint32_t base = sb + OFF_KVS + slab * KVS_BYTES + pos * 128;
  uint32_t kk[2][4][4], vv[2][4];
  mbar_wait(sb + OFF_BAR + 8 * (B_KV + slab), 0);
#pragma unroll
  for (int h = 0; h < 2; h++) {
#pragma unroll
    for (int j = 0; j < 4; j++) {
      const uint32_t a = base + 128 * j;
      ldsm4t(kk[h][j], a + (((w + 4 * h) ^ ((a >> 7) & 7)) << 4));
    }
    const uint32_t a = base + KVS_V;
    ldsm4t(vv[h], a + (((w + 4 * h) ^ ((a >> 7) & 7)) << 4));
  }
#pragma unroll
  for (int h = 0; h < 2; h++) {
    uint32_t (&k)[4][4] = kk[h];
    uint32_t (&v)[4] = vv[h];
    const uint32_t w0 = __byte_perm(sw[h].x, 0, 0x1010), w1 = __byte_perm(sw[h].x, 0, 0x3232);
    const uint32_t w2 = __byte_perm(sw[h].y, 0, 0x1010), w3 = __byte_perm(sw[h].y, 0, 0x3232);
#pragma unroll
    for (int m = 0; m < 4; m++)
      v[m] = bmul(badd(badd(badd(bmul(k[0][m], w3), bmul(k[1][m], w2)), bmul(k[2][m], w1)), bmul(k[3][m], w0)), v[m]);
    uint32_t a[4];
#pragma unroll
    for (int m = 0; m < 4; m++) a[m] = (t & 1) ? v[(m + 3) & 3] : v[m];
    res[h] = (t & 2) ? make_uint4(a[2], a[3], a[0], a[1]) : make_uint4(a[0], a[1], a[2], a[3]);
  }
}

__device__ __forceinline__ void prep_gate(const Params& p, uint32_t sb, int b, int w, int lane) {
  uint2 gw[5], x[4][5];
#pragma unroll
  for (int j = 0; j < 5; j++) gw[j] = ldg64(reinterpret_cast<const uint2*>(p.gate_w) + lane + 32 * j);
#pragma unroll
  for (int i = 0; i < 4; i++)
#pragma unroll
    for (int j = 0; j < 5; j++)
      x[i][j] = ldg64(reinterpret_cast<const uint2*>(p.q) + (16 * b + 4 * w + i) * (DIM / 4) + lane + 32 * j);
  float s[4];
#pragma unroll
  for (int i = 0; i < 4; i++) {
    s[i] = 0.f;
#pragma unroll
    for (int j = 0; j < 5; j++) {
      const uint32_t m0 = bmul(x[i][j].x, gw[j].x), m1 = bmul(x[i][j].y, gw[j].y);
      s[i] += (bf_lo(m0) + bf_hi(m0)) + (bf_lo(m1) + bf_hi(m1));
    }
  }
  const bool h = lane & 16, q = lane & 8;
  const float a = (h ? s[2] : s[0]) + __shfl_xor_sync(0xffffffffu, h ? s[0] : s[2], 16);
  const float c = (h ? s[3] : s[1]) + __shfl_xor_sync(0xffffffffu, h ? s[1] : s[3], 16);
  float z = (q ? c : a) + __shfl_xor_sync(0xffffffffu, q ? a : c, 8);
#pragma unroll
  for (int o = 4; o > 0; o >>= 1) z += __shfl_xor_sync(0xffffffffu, z, o);
  z = bf_lo(pack2(z, 0.f));
  z = bf_lo(pack2(__fdividef(1.f, 1.f + __expf(-z)), 0.f));
  mbar_wait(sb + OFF_BAR + 8 * B_S3, 0);
  if ((lane & 7) == 0) asm volatile("st.shared.f32 [%0], %1;" ::"r"(sb + OFF_GATE + 64 * (b & 7) + 16 * w + (lane >> 1)), "f"(z) : "memory");
  fence_async_smem();
}

__device__ __forceinline__ uint32_t bmax(uint32_t a, uint32_t b) {
  uint32_t d;
  asm("max.bf16x2 %0, %1, %2;" : "=r"(d) : "r"(a), "r"(b));
  return d;
}
__device__ __forceinline__ void softmax_two(const float (&l)[2][2], uint32_t& p0, uint32_t& p1) {
  constexpr float kScale = 0.22360679774997896f, kLog2e = 1.4426950408889634f;
  const uint32_t r0 = pack2(l[0][0], l[1][0]), r1 = pack2(l[0][1], l[1][1]);
  const uint32_t x0 = pack2(bf_lo(r0) * kScale, bf_hi(r0) * kScale), x1 = pack2(bf_lo(r1) * kScale, bf_hi(r1) * kScale);
  uint32_t m = bmax(x0, x1);
  m = bmax(m, __shfl_xor_sync(0xffffffffu, m, 1));
  m = bmax(m, __shfl_xor_sync(0xffffffffu, m, 2));
  const float m0 = bf_lo(m) * kLog2e, m1 = bf_hi(m) * kLog2e;
  p0 = pack2(ex2(bf_lo(x0) * kLog2e - m0), ex2(bf_lo(x1) * kLog2e - m0));
  p1 = pack2(ex2(bf_hi(x0) * kLog2e - m1), ex2(bf_hi(x1) * kLog2e - m1));
}

__device__ __forceinline__ void halo_read(uint32_t (&kpv)[10], uint32_t (&vpv)[10], uint32_t (&tg)[7], const uint4* hp) {
#pragma unroll
  for (int j = 0; j < 7; j++) {
    uint32_t x0, x1, x2;
    asm volatile("ld.relaxed.gpu.global.v4.u32 {%0, %1, %2, %3}, [%4];"
                 : "=r"(x0), "=r"(x1), "=r"(x2), "=r"(tg[j]) : "l"(hp + 32 * j) : "memory");
    if (j < 4) kpv[3 * j] = x0; else vpv[3 * j - 10] = x0;
    if (j < 3) kpv[3 * j + 1] = x1; else vpv[3 * j - 9] = x1;
    if (j < 3) kpv[3 * j + 2] = x2; else if (j < 6) vpv[3 * j - 8] = x2;
  }
}

template <int ROT>
__device__ __forceinline__ void pack_qkv(const float* acc, uint32_t (&qlo)[10], uint32_t (&qhi)[10], uint32_t (&klo)[10],
                                         uint32_t (&khi)[10], uint32_t (&vlo)[10], uint32_t (&vhi)[10]) {
#pragma unroll
  for (int j = 0; j < 10; j++) {
    const int x = (j + ROT) % 10, tq = x < 8 ? x : 16 + x, tk = x < 8 ? 8 + x : 18 + x, tv = x < 8 ? 16 + x : 20 + x;
    khi[j] = pack2(acc[4 * tk + 2], acc[4 * tk + 3]);
    vhi[j] = movm(pack2(acc[4 * tv + 2], acc[4 * tv + 3]));
    qlo[j] = pack2(acc[4 * tq], acc[4 * tq + 1]);
    qhi[j] = pack2(acc[4 * tq + 2], acc[4 * tq + 3]);
    klo[j] = pack2(acc[4 * tk], acc[4 * tk + 1]);
    vlo[j] = pack2(acc[4 * tv], acc[4 * tv + 1]);
    asm volatile("" : "+r"(khi[j]), "+r"(qlo[j]), "+r"(qhi[j]), "+r"(klo[j]), "+r"(vlo[j]));
  }
}

template <int ROT> __device__ __forceinline__ void halo_send(const float* acc, uint4* ho, uint32_t tag) {
#pragma unroll
  for (int j = 0; j < 7; j++) {
    uint32_t x[3];
#pragma unroll
    for (int e = 0; e < 3; e++) {
      const int i = 3 * j + e, y = (i % 10 + ROT) % 10, tk = y < 8 ? 8 + y : 18 + y, tv = y < 8 ? 16 + y : 20 + y;
      x[e] = i < 10 ? pack2(acc[4 * tk + 2], acc[4 * tk + 3]) : i < 20 ? movm(pack2(acc[4 * tv + 2], acc[4 * tv + 3])) : 0u;
    }
    asm volatile("st.relaxed.gpu.global.v4.u32 [%0], {%1, %2, %3, %4};" ::"l"(ho + 32 * j), "r"(x[0]), "r"(x[1]), "r"(x[2]), "r"(tag) : "memory");
  }
}

__device__ __forceinline__ void attention(float* acc, uint32_t sb, int b, int par, int w, int lane, uint32_t tag) {
  const int g = lane >> 2, t = lane & 3;
  uint32_t klo[10], khi[10], vlo[10], vhi[10], qlo[10], qhi[10], kpv[10], vpv[10];
  if (w == 3 && b < NCTA - 8) {
    uint4* ho = g_halo + (b * 2 + par) * 224 + lane;
    if (tail_first(b & 7)) halo_send<8>(acc, ho, tag);
    else halo_send<0>(acc, ho, tag);
    TSIF(par == 0, 76);
    pin<120>(acc);
  }
  if (tail_first(b & 7)) pack_qkv<8>(acc, qlo, qhi, klo, khi, vlo, vhi);
  else pack_qkv<0>(acc, qlo, qhi, klo, khi, vlo, vhi);
  const uint32_t xa = sb + OFF_KVX + (par * 3) * 2560 + lane * 16;
  if (w < 3) {
    sts128(xa + w * 2560, khi[0], khi[1], khi[2], khi[3]);
    sts128(xa + w * 2560 + 512, khi[4], khi[5], khi[6], khi[7]);
    sts128(xa + w * 2560 + 1024, khi[8], khi[9], vhi[0], vhi[1]);
    sts128(xa + w * 2560 + 1536, vhi[2], vhi[3], vhi[4], vhi[5]);
    sts128(xa + w * 2560 + 2048, vhi[6], vhi[7], vhi[8], vhi[9]);
  }
  TSIF(par == 0 && w == 1, 64);
#pragma unroll
  for (int j = 0; j < 10; j++) vlo[j] = movm(vlo[j]);
  const bool far0 = 2 * t > g, far1 = 2 * t + 1 > g;
  const uint32_t mfar = (far0 ? 0x0000FFFFu : 0u) | (far1 ? 0xFFFF0000u : 0u);
  float slo[4][2], lg[2][2];
  uint32_t phi[4], plo[4], qml[4], qmh[4];
#pragma unroll
  for (int h = 0; h < 4; h++) {
    const int f = h == 0 ? 0 : h == 1 ? 3 : h == 2 ? 5 : 8, hf = h < 2 ? 2 : 7;
    const bool mine = (h & 1) ? t >= 2 : t < 2;
    qml[h] = mine ? qlo[hf] : 0u;
    qmh[h] = mine ? qhi[hf] : 0u;
    float a[4] = {0.f, 0.f, 0.f, 0.f}, c[4] = {0.f, 0.f, 0.f, 0.f};
    mma16816(a, qlo[f], qhi[f], qlo[f + 1], qhi[f + 1], klo[f], klo[f + 1]);
    mma16816(c, qlo[f], qhi[f], qlo[f + 1], qhi[f + 1], khi[f], khi[f + 1]);
    mma1688(a, qml[h], qmh[h], klo[hf]);
    mma1688(c, qml[h], qmh[h], khi[hf]);
    slo[h][0] = a[0];
    slo[h][1] = a[1];
    lg[h & 1][0] = far0 ? a[2] : c[2];
    lg[h & 1][1] = far1 ? a[3] : c[3];
    if (h & 1) softmax_two(lg, phi[h - 1], phi[h]);
  }
  TSIF(par == 0 && w == 1, 65);
  wg_sync(1 + par);
  TSIF(par == 0 && w == 1, 66);
  const bool nohist = (w == 0) && (b < 8);
  const uint4* hp = g_halo + ((b - 8) * 2 + par) * 224 + lane;
  uint32_t tg[7];
  if (w > 0) {
    const uint4 v0 = lds128(xa + (w - 1) * 2560), v1 = lds128(xa + (w - 1) * 2560 + 512), v2 = lds128(xa + (w - 1) * 2560 + 1024);
    const uint4 v3 = lds128(xa + (w - 1) * 2560 + 1536), v4 = lds128(xa + (w - 1) * 2560 + 2048);
    kpv[0] = v0.x; kpv[1] = v0.y; kpv[2] = v0.z; kpv[3] = v0.w; kpv[4] = v1.x; kpv[5] = v1.y; kpv[6] = v1.z; kpv[7] = v1.w;
    kpv[8] = v2.x; kpv[9] = v2.y; vpv[0] = v2.z; vpv[1] = v2.w; vpv[2] = v3.x; vpv[3] = v3.y; vpv[4] = v3.z; vpv[5] = v3.w;
    vpv[6] = v4.x; vpv[7] = v4.y; vpv[8] = v4.z; vpv[9] = v4.w;
  } else if (nohist) {
#pragma unroll
    for (int j = 0; j < 10; j++) kpv[j] = vpv[j] = 0u;
  } else {
    TSIF(par == 0, 77);
    halo_read(kpv, vpv, tg, hp);
  }
  if (w == 0 && !nohist) {
    int spins = 0;
    while (true) {
      bool ok = true;
#pragma unroll
      for (int j = 0; j < 7; j++) ok = ok && tg[j] == tag;
      if (__all_sync(0xffffffffu, ok) || ++spins > SPIN_LIMIT) break;
      halo_read(kpv, vpv, tg, hp);
    }
    TSIF(par == 0, 79);
  }
#pragma unroll
  for (int h = 0; h < 4; h++) {
    const int f = h == 0 ? 0 : h == 1 ? 3 : h == 2 ? 5 : 8, hf = h < 2 ? 2 : 7;
    float a[4] = {0.f, 0.f, 0.f, 0.f};
    mma16816(a, qlo[f], qhi[f], qlo[f + 1], qhi[f + 1], kpv[f], kpv[f + 1]);
    mma1688(a, qml[h], qmh[h], kpv[hf]);
    const float ninf = __int_as_float(0xff800000);
    lg[h & 1][0] = far0 ? (nohist ? ninf : a[0]) : slo[h][0];
    lg[h & 1][1] = far1 ? (nohist ? ninf : a[1]) : slo[h][1];
    if (h & 1) softmax_two(lg, plo[h - 1], plo[h]);
  }
  TSIF(par == 0 && w <= 1, 67 + w);
  uint32_t ov[20];
#pragma unroll
  for (int hp = 0; hp < 2; hp++) {
    const int hf = hp ? 7 : 2;
    float sh[4] = {0.f, 0.f, 0.f, 0.f}, i0 = 0.f, i1 = 0.f;
#pragma unroll
    for (int e = 0; e < 2; e++) {
      const int h = 2 * hp + e, f = h == 0 ? 0 : h == 1 ? 3 : h == 2 ? 5 : 8;
      const uint32_t a0 = plo[h] & mfar, a2 = plo[h] & ~mfar, a3 = phi[h] & mfar, c1 = phi[h] & ~mfar;
      float sum[4] = {0.f, 0.f, 0.f, 0.f};
      mma1688(sum, plo[h], phi[h], 0x3F803F80u);
      const float r0 = rcp(sum[0]), r1 = rcp(sum[2]);
#pragma unroll
      for (int j = f; j < f + 2; j++) {
        float o[4] = {0.f, 0.f, 0.f, 0.f};
        mma16816(o, a0, 0u, a2, a3, vpv[j], vlo[j]);
        mma1688(o, 0u, c1, vhi[j]);
        ov[2 * j] = pack2(o[0] * r0, o[1] * r0);
        ov[2 * j + 1] = pack2(o[2] * r1, o[3] * r1);
      }
      const bool mine = e ? g >= 4 : g < 4;
      mma16816(sh, a0, 0u, a2, a3, mine ? vpv[hf] : 0u, mine ? vlo[hf] : 0u);
      mma1688(sh, 0u, c1, mine ? vhi[hf] : 0u);
      if (e == 0 || t >= 2) {
        i0 = r0;
        i1 = r1;
      }
    }
    ov[2 * hf] = pack2(sh[0] * i0, sh[1] * i0);
    ov[2 * hf + 1] = pack2(sh[2] * i1, sh[3] * i1);
  }
  TS(32 + 4 * par + w);
  mbar_wait(sb + OFF_BAR + 8 * B_P1, 0);
  const uint32_t oa = sb + OFF_OA + (lane >> 4) * 2048 + (32 * w + 2 * (lane & 15) + par) * 16;
#pragma unroll
  for (int j = 0; j < 5; j++) stsm4(oa + 4096 * j, ov + 4 * j);
  TSIF(par == 0 && w == 0, 120);
  fence_async_smem();
  TSIF(par == 0 && w == 0, 121);
  __syncwarp();
  if (lane == 0) mbar_arrive(sb + OFF_BAR + 8 * B_ATTN);
  TSM(w == 0 || w == 2, 122 + par + (w == 2 ? 3 : 0));
}

struct Maps {
  CUtensorMap x, wm, wt, k, v, y, wo, qm, qt, om, ot;
};

__device__ __forceinline__ void load_stage(uint32_t sb, int kb, int b, const Maps& m) {
  const uint32_t st = sb + (kb & 3) * STAGE_BYTES, bar = sb + OFF_BAR + 8 * (B_FULL1 + (kb & 3));
  const int r = b >> 3, hg = b & 7, slab = kb - KV_KB;
  const bool kv = slab >= 0 && slab < 5;
  const uint32_t kbar = sb + OFF_BAR + 8 * (B_KV + slab), dst = sb + OFF_KVS + slab * KVS_BYTES;
  mbar_expect_tx(bar, STAGE_BYTES);
  if (kv) mbar_expect_tx(kbar, KVS_BYTES);
  tma_3d(st, &m.x, 64 * kb, 64 * r, 0, bar);
  tma_3d(st + ST_W, &m.wm, 80 * hg + (tail_first(hg) ? 16 : 0), 64 * kb, 0, bar);
  tma_3d(st + ST_WT, &m.wt, 80 * hg + (tail_first(hg) ? 0 : 64), 64 * kb, 0, bar);
  if (kv) tma_3d(dst, &m.k, 0, 32 * (b >> 1) - 3, 2 * slab + (b & 1), kbar);
  if (kv) tma_3d(dst + KVS_V, &m.v, 0, 32 * (b >> 1), 2 * slab + (b & 1), kbar);
}

__global__ void __launch_bounds__(NTHR, 1) fused_kernel(const __grid_constant__ Maps m, const Params p) {
  extern __shared__ __align__(1024) uint8_t smem[];
  const uint32_t sb = (uint32_t)__cvta_generic_to_shared(smem);
  const uint32_t bars = sb + OFF_BAR;
  const int tid = threadIdx.x, lane = tid & 31;
  int b = blockIdx.x;
  b = (((b & 63) >> 3) * 2 + (b & 1)) * 8 + (((b < 64 ? 0x6521 : 0x7430) >> (4 * ((b >> 1) & 3))) & 7);
  const int r = b >> 3, hg = b & 7;

  if (tid == T_ISSUE) {
    TSM(true, 0);
    mbar_init(bars + 8 * B_F0, 1);
    fence_async_smem();
    mbar_expect_tx(bars + 8 * B_F0, ST_WT);
    tma_3d(sb, &m.x, 0, 64 * r, 0, bars + 8 * B_F0);
    tma_3d(sb + ST_W, &m.wm, 80 * hg + (tail_first(hg) ? 16 : 0), 0, 0, bars + 8 * B_F0);
#pragma unroll
    for (int i = 0; i < 4; i++) mbar_init(bars + 8 * (B_FULL1 + i), 1);
    fence_async_smem();
    mbar_expect_tx(bars + 8 * B_FULL1, STAGE_BYTES - ST_WT);
    tma_3d(sb + ST_WT, &m.wt, 80 * hg + (tail_first(hg) ? 0 : 64), 0, 0, bars + 8 * B_FULL1);
    load_stage(sb, 1, b, m);
  } else if (tid == T_INIT) {
#pragma unroll
    for (int i = 0; i < B_F0; i++) mbar_init(bars + 8 * i, i < B_GATE ? 8 : i < B_CVD ? 4 : i == B_CVD ? 20 : 1);
    fence_async_smem();
  }
  const int warp = __shfl_sync(0xffffffffu, tid >> 5, 0), wg = warp >> 2, w = warp & 3;
  __syncthreads();

  if (wg == 3) {
    asm volatile("setmaxnreg.dec.sync.aligned.u32 56;");
    if (w == 0) {
      if (lane == 0) {
#pragma unroll 1
        for (int kb = 2; kb < 10; kb++) {
          if (kb >= 4) mbar_wait(bars + 8 * (kb == 7 ? B_E3 : B_EMPTY1 + (kb & 3)), (kb >> 3) & 1);
          TSIF(kb >= 4, 44 + kb);
          load_stage(sb, kb, b, m);
          TSIF(kb == 3, 60);
          if (kb == TRIG_KB) mbar_arrive(bars + 8 * B_LAST);
        }
        mbar_wait(bars + 8 * B_WOP, 0);
        mbar_wait(bars + 8 * WL_TRIG, 0);
        mbar_wait(bars + 8 * B_EPOCH, 0);
        flag_wait(g_cnt + C_W + 32 * hg, (lds32(sb + OFF_EPOCH) + 1) * 16);
        TS(30);
#pragma unroll 1
        for (int j = 0; j < 8; j++) {
          if (j >= 6) mbar_wait(bars + 8 * (B_EMPTY2 + j - 6), 0);
          if (j == 4) mbar_wait(bars + 8 * B_ATTN, 0);
          TSIF(j >= 6, 100 + j);
          mbar_expect_tx(bars + 8 * (B_FULL2 + j), j == 0 ? WO_BYTES : j == 5 ? O_BYTES + WO_BYTES + 512 : O_BYTES + WO_BYTES);
          bulk_load(sb + off_w(j), g_WO + (hg * 8 + step_src(hg, j)) * 800, WO_BYTES, bars + 8 * (B_FULL2 + j));
        }
        if (!Q_SWAP) {
          mbar_wait(bars + 8 * (B_EMPTY2 + 3), 0);
          mbar_expect_tx(bars + 8 * B_QF, O_BYTES);
          tma_2d(sb + OFF_QS, &m.qm, 80 * hg, 128 * r, bars + 8 * B_QF);
          tma_2d(sb + OFF_QT, &m.qt, 80 * hg + 64, 128 * r, bars + 8 * B_QF);
        }
      }
    } else if (w == 1) {
      unsigned epoch = 0;
      if (lane == 0) {
        epoch = atomicAdd(g_cnt + C_LAUNCH, 1u) / NCTA;
        asm volatile("st.shared.u32 [%0], %1;" ::"r"(sb + OFF_EPOCH), "r"(epoch) : "memory");
        mbar_arrive(bars + 8 * B_EPOCH);
        mbar_wait(bars + 8 * B_KVD, 0);
        mbar_expect_tx(bars + 8 * B_HB, 5 * 4096);
#pragma unroll 1
        for (int c = 0; c < 5; c++) {
          if (c == 3) mbar_wait(bars + 8 * B_S3, 0);
          bulk_load(sb + off_ch(c) + U_BYTES, p.ssm_k + (5 * b + c) * SEQ, 4096, bars + 8 * B_HB);
        }
#pragma unroll
        for (int c = 0; c < 4; c++) mbar_expect_tx(bars + 8 * (B_U + c), c < 3 ? U_BYTES : 2 * U_BYTES);
        const uint4* usrc = g_U + 5 * b * U_PITCH;
        mbar_wait(bars + 8 * B_USIG, 0);
        flag_wait(g_cnt + C_PREP + 32 * (b & 15), (epoch + 1) * NCTA);
        TS(23);
#pragma unroll
        for (int c = 0; c < 5; c++) {
          if (c == 3) mbar_wait(bars + 8 * (B_U + 2), 0);
          bulk_load(sb + off_ch(c), usrc + c * U_PITCH, U_BYTES, bars + 8 * (B_U + (c < 3 ? c : 3)));
          TSIF(c == 0 || c == 4, 116 + (c >> 2));
        }
      }
      epoch = __shfl_sync(0xffffffffu, epoch, 0);
      if (lane < 8) {
        const int src = (b & ~7) | step_src(hg, lane);
        mbar_wait(bars + 8 * B_ATTN, 0);
        TS(20);
        bool seen = false;
#pragma unroll 1
        for (int spins = 0; spins < SPIN_LIMIT; spins++) {
          const bool now = !seen && (int)(flag_read(g_cnt + C_O + 32 * src) - (epoch + 1)) >= 0;
          if (now && lane >= 1 && lane < 4) bulk_load(sb + off_o(lane), g_O + src * 1280, O_BYTES, bars + 8 * (B_FULL2 + lane));
          seen = seen || now;
          if (__all_sync(0xff, seen)) break;
        }
        TS(21);
        if (lane == 5) bulk_load(sb + OFF_GATE, g_gate + 128 * r, 512, bars + 8 * (B_FULL2 + 5));
#pragma unroll 1
        for (int j = 4; j < 8; j++) {
          if (lane == j) {
            mbar_wait(bars + 8 * (j < 6 ? B_C34 : B_EMPTY2 + j - 6), 0);
            bulk_load(sb + off_o(j), g_O + src * 1280, O_BYTES, bars + 8 * (B_FULL2 + j));
          }
          __syncwarp(0xff);
        }
        TS(22);
      }
    } else if (w == 2) {
      mbar_wait(bars + 8 * B_PREP, 0);
      flag_signal(g_cnt + C_PREP, 16, lane);
      TS(25);
      if (lane == 0) {
        mbar_arrive(bars + 8 * B_USIG);
        mbar_expect_tx(bars + 8 * B_ORB, O_BYTES + 64);
        mbar_wait(bars + 8 * B_GATE, 0);
        publish(g_gate + 16 * b, sb + OFF_GATE + 64 * hg, 64, bars + 8 * B_ORB);
        mbar_wait(bars + 8 * B_ATTN, 0);
        publish(g_O + b * 1280, sb + OFF_OA, O_BYTES, bars + 8 * B_ORB);
        TS(74);
        mbar_wait(bars + 8 * B_ORB, 0);
        flag_bump(g_cnt + C_O + 32 * b);
        TS(26);
        mbar_arrive(bars + 8 * B_OSIG);
      }
    } else {
      if (lane == 0) {
        uint4* dst = g_WO + (hg * 8 + (r >> 1)) * 800 + (r & 1) * 80;
        mbar_wait(bars + 8 * B_S3, 0);
        asm volatile("cp.async.bulk.prefetch.L2.global [%0], 6400;" ::"l"(p.wo + b * 3200) : "memory");
        mbar_wait(bars + 8 * B_P1, 0);
        mbar_wait(bars + 8 * WB_TRIG, 0);
        mbar_expect_tx(bars + 8 * B_WST, WO_BYTES / 2);
        tma_3d(sb + OFF_WA, &m.wo, 0, 40 * r, 5 * hg, bars + 8 * B_WST);
        mbar_wait(bars + 8 * B_WST, 0);
#pragma unroll 1
        for (int n = 0; n < 5; n++) bulk_store(dst + 160 * n, sb + OFF_WA + 1280 * n, 1280);
        bulk_wait_read();
        mbar_expect_tx(bars + 8 * B_WST, WO_BYTES / 2);
#pragma unroll 1
        for (int n = 0; n < 5; n++) bulk_load(sb + OFF_WA + 1280 * n, dst + 160 * n, 1280, bars + 8 * B_WST);
        mbar_wait(bars + 8 * B_WST, 1);
        flag_bump(g_cnt + C_W + 32 * hg);
        mbar_arrive(bars + 8 * B_WOP);
        TS(71);
        mbar_expect_tx(bars + 8 * B_C34, 3 * U_BYTES);
        mbar_expect_tx(bars + 8 * B_YRB, 2 * U_BYTES);
#pragma unroll 1
        for (int c = 0; c < 5; c++) {
          mbar_wait(bars + 8 * (B_YST + c), 0);
          publish(g_U + (5 * b + c) * U_PITCH, sb + off_ch(c), U_BYTES, bars + 8 * (c < 3 ? B_C34 : B_YRB));
        }
        TS(75);
        mbar_wait(bars + 8 * B_C34, 0);
        mbar_wait(bars + 8 * B_YRB, 0);
        flag_bump(g_cnt + C_Y + 32 * (b >> 4));
        TS(27);
        mbar_arrive(bars + 8 * B_YSIG);
        if (Q_SWAP) {
          mbar_expect_tx(bars + 8 * B_QF, O_BYTES);
          tma_2d(sb + OFF_QS, &m.qm, 80 * hg, 128 * r, bars + 8 * B_QF);
          tma_2d(sb + OFF_QT, &m.qt, 80 * hg + 64, 128 * r, bars + 8 * B_QF);
        }
        mbar_expect_tx(bars + 8 * B_YFULL, 20480);
        flag_wait(g_cnt + C_Y + 32 * hg, (lds32(sb + OFF_EPOCH) + 1) * 16);
        TS(24);
        if (Q_SWAP) mbar_wait(bars + 8 * (B_EMPTY2 + Q_SWAP), 0);
        tma_2d(sb + OFF_YT, &m.y, 128 * r, 80 * hg, bars + 8 * B_YFULL);
        tma_2d(sb + OFF_YT + 10240, &m.y, 128 * r + 64, 80 * hg, bars + 8 * B_YFULL);
      }
    }
  } else {
    asm volatile("setmaxnreg.inc.sync.aligned.u32 152;");
    if (wg < 2) {
      float acc[120];
#pragma unroll
      for (int i = 0; i < 120; i++) acc[i] = 0.f;
      const uint32_t da = desc_lo(sb + wg * 8192, 16), db = desc_lo(sb + ST_W, 8192), dc = desc_lo(sb + ST_WT, 2048);
      mbar_wait(bars + 8 * B_F0, 0);
      TSIF(w == 0 && wg == 0, 1);
      wg_fence();
#pragma unroll
      for (int k = 0; k < 4; k++) WgSST<192>::mma<HI_SW128, HI_SW128>(acc, da + 2 * k, db + 128 * k, 1);
      wg_commit();
      mbar_wait(bars + 8 * B_FULL1, 0);
      wg_fence();
#pragma unroll
      for (int k = 0; k < 4; k++) WgSST<48>::mma<HI_SW128, HI_SW32>(acc + 96, da + 2 * k, dc + 32 * k, 1);
      wg_commit();
#pragma unroll 1
      for (int kb = 1; kb < 10; kb++) {
        mbar_wait(bars + 8 * (B_FULL1 + (kb & 3)), (kb >> 2) & 1);
        const uint32_t so = (kb & 3) * (STAGE_BYTES >> 4);
        wg_fence();
#pragma unroll
        for (int k = 0; k < 4; k++) {
          WgSST<192>::mma<HI_SW128, HI_SW128>(acc, da + so + 2 * k, db + so + 128 * k, 1);
          WgSST<48>::mma<HI_SW128, HI_SW32>(acc + 96, da + so + 2 * k, dc + so + 32 * k, 1);
        }
        wg_commit();
        wg_wait<1>();
        if (lane == 0) mbar_arrive(bars + 8 * (kb == 4 ? B_E3 : B_EMPTY1 + ((kb - 1) & 3)));
      }
      mbar_wait(bars + 8 * B_EPOCH, 0);
      const uint32_t tag = lds32(sb + OFF_EPOCH) + 1;
      mbar_wait(bars + 8 * B_S3, 0);
      wg_wait<0>();
      pin<120>(acc);
      if (lane == 0) mbar_arrive(bars + 8 * B_P1);
      TSM(w == 0, 3 + wg);
      attention(acc, sb, b, wg, w, lane, tag);
    } else {
      const int tw = tid & 127, chl = 64 * (b & 1) + 8 * w + (lane >> 2);
      uint4* up = g_U + chl * U_PITCH + ((4 * (b >> 1) + (lane & 3)) ^ ((b >> 2) & 1));
      uint2 sw[10];
      uint32_t dv = 0;
      if (lane < 5) dv = __ldg(reinterpret_cast<const unsigned short*>(p.ssm_D) + 5 * b + lane);
#pragma unroll
      for (int i = 0; i < 10; i++) sw[i] = ldg64(reinterpret_cast<const uint2*>(p.shift_k) + chl + 128 * (i >> 1) + 32 * (i & 1));
      uint32_t tab[12];
      uint32_t tt[2];
      fft_tables(tab, tw);
      fft_twiddles(tt, tw);
      uint4 res[10];
#pragma unroll
      for (int i = 0; i < 10; i++) res[i] = make_uint4(0, 0, 0, 0);
#pragma unroll 1
      for (int slab = 0; slab < 5; slab++) {
#pragma unroll
        for (int i = 0; i < 8; i++) res[i] = res[i + 2];
        prep_slab(res + 8, sw, sb, slab, w, lane);
        TSIF(w == 0, 99 + 4 * slab);
#pragma unroll
        for (int i = 0; i < 8; i++) sw[i] = sw[i + 2];
      }
      TSIF(w == 0, 28);
      __syncwarp();
      if (lane == 0) mbar_arrive(bars + 8 * B_KVD + ((res[8].x ^ res[9].x) & p.zero));
      mbar_wait(bars + 8 * B_KVD, 0);
      fft_tables_store(tab, sb, tw);
      mbar_wait(bars + 8 * B_LAST, 0);
#pragma unroll
      for (int i = 0; i < 10; i++) up[(128 * (i >> 1) + 32 * (i & 1)) * U_PITCH] = res[i];
      __syncwarp();
      if (lane == 0) mbar_arrive(bars + 8 * B_PREP);
      TSIF(w == 0, 5);
      mbar_wait(bars + 8 * B_LAST, 0);
      prep_gate(p, sb, b, w, lane);
      __syncwarp();
      if (lane == 0) mbar_arrive(bars + 8 * B_GATE);
      TSIF(w == 0, 72);
      mbar_wait(bars + 8 * B_HB, 0);
      TSIF(w == 0, 2);
      const uint32_t ha = sb + U_BYTES + ((tw >> 3) * 16 + 8 + (tw & 7)) * 16;
      uint4 hv[5];
#pragma unroll
      for (int c = 0; c < 5; c++) hv[c] = lds128(ha + off_ch(c));
      __syncwarp();
#pragma unroll
      for (int c = 0; c < 5; c++) sts128((ha ^ 16) + off_ch(c), hv[c].x, hv[c].y, hv[c].z, hv[c].w);
      asm volatile("st.shared.v2.u32 [%0], {%1, %2};" ::"r"(sb + OFF_TT + 8 * tw), "r"(tt[0]), "r"(tt[1]) : "memory");
      if (tw < 5) asm volatile("st.shared.f32 [%0], %1;" ::"r"(sb + OFF_D + 4 * tw), "f"(bf_lo(dv) * 0.125f) : "memory");
      fence_async_smem();
      __syncwarp();
      if (lane == 0) mbar_arrive(bars + 8 * B_HA);
      TSIF(w == 0, 6);
    }

    FftConst fc;
    TSM(w == 0 && wg == 0, 104);
    mbar_wait(bars + 8 * B_HA, 0);
    fft_matrices(fc, sb, w, lane);
    TSM(w == 0 && wg == 0, 105);
    TSM(w == 0 && wg == 2, 124);
#pragma unroll 1
    for (uint32_t tasks = wg == 0 ? TASK0 : wg == 1 ? TASK1 : TASK2; tasks; tasks >>= 4) {
      const int c = (tasks & 7) - 1;
      conv_channel(fc, sb, c, wg, w, lane);
      if (lane == 0) mbar_arrive(bars + 8 * (B_YST + c));
      TSM(w == 0, 10 + c);
    }

    if (wg < 2) {
      const int g = lane >> 2;
      float acc[40];
#pragma unroll
      for (int i = 0; i < 40; i++) acc[i] = 0.f;
      const uint32_t da = desc_lo(sb + wg * 1024, 2048), db = desc_lo(sb, 2560);
      mbar_wait(bars + 8 * B_ORB, 0);
      mbar_wait(bars + 8 * B_FULL2, 0);
      mbar_wait(bars + 8 * B_CVD, 0);
      TSM(w == 0, 15 + wg);
#pragma unroll 1
      for (int j = 0; j < 8; j++) {
        mbar_wait(bars + 8 * (B_FULL2 + j), 0);
        TSM(w == 0 && wg == 0, 44 + (j < 4 ? j : j + 6));
        const uint32_t oa = da + (off_o(j) >> 4), ob = db + (off_w(j) >> 4);
        wg_fence();
#pragma unroll
        for (int k = 0; k < 5; k++) WgSST<80>::mma<HI_NONE, HI_SW32>(acc, oa + 256 * k, ob + 32 * k, 1);
        wg_commit();
        wg_wait<1>();
        if (j >= 1 && j <= 4 && lane == 0) mbar_arrive(bars + 8 * (B_EMPTY2 + j - 1));
      }
      TSIF(w == 0 && wg == 0, 113);
      const int tr = 64 * wg + 16 * w + (lane & 15);
      const uint32_t fm = sb + OFF_QS + tr * 128, fx = (lane >> 4) ^ (tr & 7);
      const uint32_t ft = sb + OFF_QT + tr * 32 + (((lane >> 4) ^ (tr >> 2)) & 1) * 16;
      const float g0 = __uint_as_float(lds32(sb + OFF_GATE + (64 * wg + 16 * w + g) * 4));
      const float g1 = __uint_as_float(lds32(sb + OFF_GATE + (64 * wg + 16 * w + 8 + g) * 4));
      const uint32_t ga = pack2(g0, g0), gb = pack2(g1, g1);
      const uint32_t na = pack2(1.f - g0, 1.f - g0), nb = pack2(1.f - g1, 1.f - g1);

      uint32_t qf[20];
      mbar_wait(bars + 8 * B_QF, 0);
      TSM(w == 0 && wg == 0, 99);
#pragma unroll
      for (int j = 0; j < 5; j++) ldsm4(qf + 4 * j, j < 4 ? fm + ((fx ^ (2 * j)) << 4) : ft);
#pragma unroll
      for (int i = 0; i < 20; i++) {
        qf[i] = bmul((i & 1) ? gb : ga, qf[i]);
        asm volatile("" : "+r"(qf[i]));
      }

      wg_wait<0>();
      pin<40>(acc);
      TSM(w == 0, 17 + wg);
      uint32_t pb[20];
#pragma unroll
      for (int j = 0; j < 10; j++) {
        pb[2 * j] = bmul(na, pack2(acc[4 * j], acc[4 * j + 1]));
        pb[2 * j + 1] = bmul(nb, pack2(acc[4 * j + 2], acc[4 * j + 3]));
        asm volatile("" : "+r"(pb[2 * j]), "+r"(pb[2 * j + 1]));
      }
      const uint32_t ya = sb + OFF_YT + wg * 10240 + ((lane >> 4) * 8 + (lane & 7)) * 128 +
                          (((2 * w + (((lane >> 3) & 1) ^ wg)) ^ (lane & 7)) << 4);
      mbar_wait(bars + 8 * B_YFULL, 0);
      TSM(w == 0 && wg == 0, 19);
#pragma unroll
      for (int j = 0; j < 5; j++) {
        uint32_t y[4];
        ldsm4t(y, ya + 2048 * j);
#pragma unroll
        for (int i = 0; i < 4; i++)
          qf[4 * j + i] = bfma(qf[4 * j + i], y[i], pb[4 * j + i]);
      }
#pragma unroll
      for (int j = 0; j < 5; j++) stsm4(j < 4 ? fm + ((fx ^ (2 * j)) << 4) : ft, qf + 4 * j);
      fence_async_smem();
      __syncwarp();
      if (lane == 0) {
        const int row = 64 * wg + 16 * w;
        asm volatile("cp.async.bulk.tensor.2d.global.shared::cta.bulk_group [%0, {%2, %3}], [%1];"
                     ::"l"(&m.om), "r"(sb + OFF_QS + row * 128), "r"(80 * hg), "r"(128 * r + row) : "memory");
        asm volatile("cp.async.bulk.tensor.2d.global.shared::cta.bulk_group [%0, {%2, %3}], [%1];"
                     ::"l"(&m.ot), "r"(sb + OFF_QT + row * 32), "r"(80 * hg + 64), "r"(128 * r + row) : "memory");
        asm volatile("cp.async.bulk.commit_group;\ncp.async.bulk.wait_group.read 0;" ::: "memory");
      }
      TSM(w == 0 || w == 3, 40 + 2 * wg + (w & 1));
    }
  }
}

typedef CUresult (*EncodeFn)(CUtensorMap*, CUtensorMapDataType, cuuint32_t, void*, const cuuint64_t*, const cuuint64_t*,
                             const cuuint32_t*, const cuuint32_t*, CUtensorMapInterleave, CUtensorMapSwizzle,
                             CUtensorMapL2promotion, CUtensorMapFloatOOBfill);

void encode(EncodeFn fn, CUtensorMap* tm, const void* base, int rank, const cuuint64_t* dims, const cuuint64_t* strides,
            const cuuint32_t* box, CUtensorMapSwizzle swz) {
  const cuuint32_t ones[3] = {1, 1, 1};
  fn(tm, CU_TENSOR_MAP_DATA_TYPE_BFLOAT16, rank, const_cast<void*>(base), dims, strides, box, ones,
     CU_TENSOR_MAP_INTERLEAVE_NONE, swz, CU_TENSOR_MAP_L2_PROMOTION_L2_128B, CU_TENSOR_MAP_FLOAT_OOB_FILL_NONE);
}

}

extern "C" void kernel_launch(void* const* d_in, const int* in_sizes, int n_in, void* d_out, int out_size) {
  (void)in_sizes; (void)n_in; (void)out_size;
  Params p;
  p.q = (const __nv_bfloat16*)d_in[0];
  p.k = (const __nv_bfloat16*)d_in[1];
  p.v = (const __nv_bfloat16*)d_in[2];
  p.shift_k = (const __nv_bfloat16*)d_in[3];
  p.ssm_k = (const __nv_bfloat16*)d_in[4];
  p.ssm_D = (const __nv_bfloat16*)d_in[5];
  p.wqkv = (const __nv_bfloat16*)d_in[7];
  p.wo = (const __nv_bfloat16*)d_in[8];
  p.gate_w = (const __nv_bfloat16*)d_in[9];
  p.out = (__nv_bfloat16*)d_out;
  p.zero = 0;

  static EncodeFn fn = nullptr;
  static void* yaddr = nullptr;
  if (!fn) {
    cudaDriverEntryPointQueryResult qr;
    void* f = nullptr;
    cudaGetDriverEntryPoint("cuTensorMapEncodeTiled", &f, cudaEnableDefault, &qr);
    fn = (EncodeFn)f;
    cudaGetSymbolAddress(&yaddr, g_U);
    cudaFuncSetAttribute(fused_kernel, cudaFuncAttributeMaxDynamicSharedMemorySize, SMEM_BYTES);
  }
  Maps m;
  {
    const cuuint64_t dims[3] = {640, 1024, 2}, st[2] = {2560, 1280};
    const cuuint32_t box[3] = {64, 64, 2};
    encode(fn, &m.x, p.q, 3, dims, st, box, CU_TENSOR_MAP_SWIZZLE_128B);
  }
  {
    const cuuint64_t dims[3] = {640, 640, 3}, st[2] = {3840, 1280};
    const cuuint32_t box[3] = {64, 64, 3}, boxt[3] = {16, 64, 3};
    encode(fn, &m.wm, p.wqkv, 3, dims, st, box, CU_TENSOR_MAP_SWIZZLE_128B);
    encode(fn, &m.wt, p.wqkv, 3, dims, st, boxt, CU_TENSOR_MAP_SWIZZLE_32B);
  }
  {
    const cuuint64_t dims[3] = {64, 2048, 10}, st[2] = {1280, 128};
    const cuuint32_t boxk[3] = {64, 35, 1}, boxv[3] = {64, 32, 1};
    encode(fn, &m.k, p.k, 3, dims, st, boxk, CU_TENSOR_MAP_SWIZZLE_128B);
    encode(fn, &m.v, p.v, 3, dims, st, boxv, CU_TENSOR_MAP_SWIZZLE_128B);
  }
  {
    const cuuint64_t dims[3] = {16, 640, 40}, st[2] = {1280, 32};
    const cuuint32_t box[3] = {16, 40, 5};
    encode(fn, &m.wo, p.wo, 3, dims, st, box, CU_TENSOR_MAP_SWIZZLE_32B);
  }
  {
    const cuuint64_t dims[2] = {2048, 640}, st[1] = {U_PITCH * 16};
    const cuuint32_t box[2] = {64, 80};
    encode(fn, &m.y, yaddr, 2, dims, st, box, CU_TENSOR_MAP_SWIZZLE_128B);
  }
  {
    const cuuint64_t dims[2] = {640, 2048}, st[1] = {1280};
    const cuuint32_t bqm[2] = {64, 128}, bqt[2] = {16, 128}, bom[2] = {64, 16}, bot[2] = {16, 16};
    encode(fn, &m.qm, p.q, 2, dims, st, bqm, CU_TENSOR_MAP_SWIZZLE_128B);
    encode(fn, &m.qt, p.q, 2, dims, st, bqt, CU_TENSOR_MAP_SWIZZLE_32B);
    encode(fn, &m.om, p.out, 2, dims, st, bom, CU_TENSOR_MAP_SWIZZLE_128B);
    encode(fn, &m.ot, p.out, 2, dims, st, bot, CU_TENSOR_MAP_SWIZZLE_32B);
  }
  fused_kernel<<<NCTA, NTHR, SMEM_BYTES>>>(m, p);
}
```

```cpp
#include <cuda.h>
#include <cuda_bf16.h>
#include <cuda_runtime.h>
#include <stdint.h>

namespace {

constexpr int SEQ = 2048, DIM = 640, NCTA = 128, NTHR = 512;

#define TRIG_KB 9
#define KV_KB 2
#define DEV_EXIT 0
#define FENCE_LO 0
#define FENCE_HI 0
#define WB_TRIG B_USIG
#define T_ISSUE 256
#define O_ALL 1
#define T_INIT 448
#define TASK0 0x3
#define TASK1 0x52
#define TASK2 0x41
#define WL_TRIG B_WOP

constexpr uint32_t STAGE_BYTES = 47104, ST_W = 16384, ST_WT = 40960;
constexpr uint32_t O_BYTES = 20480, WO_BYTES = 12800;
constexpr uint32_t OFF_OA = 0;
constexpr uint32_t OFF_QS = 3 * O_BYTES, OFF_QT = OFF_QS + 16384;
constexpr uint32_t OFF_WC = 81920;
constexpr uint32_t OFF_WA = 94720;
constexpr uint32_t OFF_GATE = 145920;
constexpr uint32_t OFF_TT = 146432;
constexpr uint32_t OFF_KVX = 148480;
constexpr uint32_t OFF_CH3 = 163840;
constexpr uint32_t CH_BYTES = 12288, U_BYTES = 4096;
constexpr uint32_t OFF_FT = 225280, OFF_GT = 229376;
constexpr uint32_t OFF_CH0 = 188416;
constexpr uint32_t OFF_KVS = OFF_CH0, KVS_V = 4480, KVS_BYTES = 8576;
constexpr uint32_t OFF_YT = 163840;
constexpr uint32_t OFF_BAR = 231936;
constexpr uint32_t SMEM_BYTES = OFF_BAR + 512;

enum : uint32_t {
  B_EMPTY1 = 0, B_S3 = 3, B_E3 = 4, B_EMPTY2 = 5, B_ATTN = 9, B_P1 = 10,
  B_GATE = 11, B_HA = 12, B_KVD = 13, B_PREP = 14, B_YST = 15,
  B_CVD = 20,
  B_FULL2 = 21, B_U = 29, B_KV = 33, B_HB = 38, B_C34 = 39, B_YRB = 40, B_YFULL = 41, B_EPOCH = 42, B_LAST = 43, B_OSIG = 44,
  B_WOP = 45, B_USIG = 46, B_WST = 47, B_QF = 48, B_ORB = 49, B_YSIG = 50,
  B_F0 = 51, B_FULL1 = 52
};
constexpr uint32_t OFF_EPOCH = OFF_BAR + 8 * 58, OFF_D = OFF_BAR + 8 * 60;
__device__ __forceinline__ uint32_t off_o(int j) { return j < 4 ? OFF_OA + j * O_BYTES : j < 6 ? OFF_CH0 + (j - 4) * O_BYTES : OFF_OA + (j - 6) * O_BYTES; }
__device__ __forceinline__ uint32_t off_w(int j) { return j < 4 ? OFF_WA + j * WO_BYTES : j == 4 ? OFF_KVX : j == 5 ? OFF_WC : OFF_WA + (j - 6) * WO_BYTES; }
__device__ __forceinline__ int step_src(int hg, int j) { return j == 0 ? hg : j <= hg ? j - 1 : j; }
__device__ __forceinline__ bool tail_first(int hg) { return (hg & 3) == 3; }
__device__ __forceinline__ uint32_t off_ch(int c) { return (c < 3 ? OFF_CH0 : OFF_CH3 - 3 * CH_BYTES) + c * CH_BYTES; }

#define U_PITCH 264
__device__ __align__(1024) uint4 g_U[DIM * U_PITCH];
__device__ uint4 g_O[NCTA * 1280];
__device__ uint4 g_WO[64 * 800];
__device__ uint4 g_halo[NCTA * 2 * 7 * 32];
__device__ __align__(128) float g_gate[SEQ];
__device__ unsigned g_cnt[32 * (1 + 2 * 16 + 8 + NCTA)];
constexpr int C_LAUNCH = 0, C_PREP = 32, C_Y = 32 * 17, C_W = 32 * 33, C_O = 32 * 41;

#define TSM(cond, slot) do { } while (0)
#define TSIF(cond, slot) do { if (__LINE__ >= FENCE_LO && __LINE__ < FENCE_HI) sched_fence(); } while (0)
__device__ __forceinline__ void sched_fence() {
  asm volatile("{\n.reg .pred p;\n.reg .u32 c;\nmov.u32 c, %%clock;\nsetp.eq.u32 p, c, 0;\n@p st.shared.u32 [%0], c;\n}"
               ::"r"(1024 + OFF_EPOCH + 4) : "memory");
}
#define TS(slot) TSIF(true, slot)

struct Params {
  const __nv_bfloat16 *q, *k, *v, *shift_k, *ssm_k, *ssm_D, *wqkv, *wo, *gate_w;
  __nv_bfloat16* out;
  uint32_t zero;
};

constexpr int SPIN_LIMIT = 1 << 17;

__device__ __forceinline__ void mbar_init(uint32_t bar, uint32_t count) {
  asm volatile("mbarrier.init.shared::cta.b64 [%0], %1;" ::"r"(bar), "r"(count) : "memory");
}
__device__ __forceinline__ void mbar_expect_tx(uint32_t bar, uint32_t bytes) {
  asm volatile("mbarrier.arrive.expect_tx.shared::cta.b64 _, [%0], %1;" ::"r"(bar), "r"(bytes) : "memory");
}
__device__ __forceinline__ void mbar_arrive(uint32_t bar) {
  asm volatile("mbarrier.arrive.shared::cta.b64 _, [%0];" ::"r"(bar) : "memory");
}
__device__ __forceinline__ void mbar_wait(uint32_t bar, uint32_t parity) {
  uint32_t ok;
  int spins = 0;
  do {
      asm volatile("{\n.reg .pred p;\nmbarrier.try_wait.parity.shared::cta.b64 p, [%1], %2;\nselp.b32 %0, 1, 0, p;\n}"
                   : "=r"(ok) : "r"(bar), "r"(parity) : "memory");
    if (++spins > SPIN_LIMIT) break;
  } while (!ok);
}
__device__ __forceinline__ bool mbar_test(uint32_t bar) {
  uint32_t ok;
  asm volatile("{\n.reg .pred p;\nmbarrier.test_wait.parity.shared::cta.b64 p, [%1], 0;\nselp.b32 %0, 1, 0, p;\n}" : "=r"(ok) : "r"(bar) : "memory");
  return ok;
}
__device__ __forceinline__ unsigned flag_read(const unsigned* p) {
  unsigned v;
  asm volatile("ld.relaxed.gpu.global.u32 %0, [%1];" : "=r"(v) : "l"(p) : "memory");
  return v;
}
__device__ __forceinline__ void flag_poll(const unsigned* p, unsigned target) {
  unsigned v;
  int spins = 0;
  do {
    asm volatile("ld.relaxed.gpu.global.u32 %0, [%1];" : "=r"(v) : "l"(p) : "memory");
    if (++spins > SPIN_LIMIT) break;
  } while ((int)(v - target) < 0);
}
__device__ __forceinline__ void flag_wait(const unsigned* p, unsigned target) {
  flag_poll(p, target);
}
__device__ __forceinline__ void flag_signal(unsigned* p, int n, int lane) {
  if (lane == 0) asm volatile("fence.release.gpu;" ::: "memory");
  __syncwarp();
  if (lane < n) asm volatile("red.relaxed.gpu.global.add.u32 [%0], 1;" ::"l"(p + 32 * lane) : "memory");
}
__device__ __forceinline__ void flag_bump(unsigned* p) {
  asm volatile("red.relaxed.gpu.global.add.u32 [%0], 1;" ::"l"(p) : "memory");
}
__device__ __forceinline__ void fence_async_smem() { asm volatile("fence.proxy.async.shared::cta;" ::: "memory"); }
__device__ __forceinline__ void wg_sync(int id) { asm volatile("bar.sync %0, 128;" ::"r"(id) : "memory"); }

__device__ __forceinline__ void tma_2d(uint32_t dst, const CUtensorMap* tm, int c0, int c1, uint32_t bar) {
  asm volatile("cp.async.bulk.tensor.2d.shared::cluster.global.mbarrier::complete_tx::bytes [%0], [%1, {%3, %4}], [%2];"
               ::"r"(dst), "l"(tm), "r"(bar), "r"(c0), "r"(c1) : "memory");
}
__device__ __forceinline__ void tma_3d(uint32_t dst, const CUtensorMap* tm, int c0, int c1, int c2, uint32_t bar) {
  asm volatile("cp.async.bulk.tensor.3d.shared::cluster.global.mbarrier::complete_tx::bytes [%0], [%1, {%3, %4, %5}], [%2];"
               ::"r"(dst), "l"(tm), "r"(bar), "r"(c0), "r"(c1), "r"(c2) : "memory");
}
__device__ __forceinline__ void bulk_load(uint32_t dst, const void* src, uint32_t bytes, uint32_t bar) {
  asm volatile("cp.async.bulk.shared::cluster.global.mbarrier::complete_tx::bytes [%0], [%1], %2, [%3];"
               ::"r"(dst), "l"(src), "r"(bytes), "r"(bar) : "memory");
}
__device__ __forceinline__ void bulk_store(void* dst, uint32_t src, uint32_t bytes) {
  asm volatile("cp.async.bulk.global.shared::cta.bulk_group [%0], [%1], %2;" ::"l"(dst), "r"(src), "r"(bytes) : "memory");
}
__device__ __forceinline__ void bulk_wait_read() {
  asm volatile("cp.async.bulk.commit_group;\ncp.async.bulk.wait_group.read 0;" ::: "memory");
}

__device__ __forceinline__ void publish(void* dst, uint32_t src, uint32_t bytes, uint32_t bar) {
  bulk_store(dst, src, bytes);
  bulk_wait_read();
  bulk_load(src, dst, bytes, bar);
}

__device__ __forceinline__ void wg_fence() { asm volatile("wgmma.fence.sync.aligned;" ::: "memory"); }
__device__ __forceinline__ void wg_commit() { asm volatile("wgmma.commit_group.sync.aligned;" ::: "memory"); }
template <int N> __device__ __forceinline__ void wg_wait() { asm volatile("wgmma.wait_group.sync.aligned %0;" ::"n"(N) : "memory"); }
__device__ __forceinline__ uint32_t desc_lo(uint32_t addr, uint32_t lbo) { return ((addr & 0x3FFFF) >> 4) | ((lbo >> 4) << 16); }
constexpr uint32_t desc_hi(uint32_t sbo, uint32_t swz) { return (sbo >> 4) | (swz << 30); }
constexpr uint32_t HI_SW128 = desc_hi(1024, 1), HI_SW64 = desc_hi(512, 2), HI_SW32 = desc_hi(256, 3), HI_NONE = desc_hi(128, 0);
template <int N> __device__ __forceinline__ void pin(float* d) {
#pragma unroll
  for (int i = 0; i < N; i++) asm volatile("" : "+f"(d[i])::"memory");
}

__device__ __forceinline__ uint32_t lds32(uint32_t a) {
  uint32_t v;
  asm volatile("ld.volatile.shared.u32 %0, [%1];" : "=r"(v) : "r"(a) : "memory");
  return v;
}
__device__ __forceinline__ uint2 ldg64(const void* a) {
  uint2 v;
  asm volatile("ld.global.nc.v2.u32 {%0, %1}, [%2];" : "=r"(v.x), "=r"(v.y) : "l"(a) : "memory");
  return v;
}
__device__ __forceinline__ void ldsm4(uint32_t* r, uint32_t a) {
  asm volatile("ldmatrix.sync.aligned.m8n8.x4.shared.b16 {%0, %1, %2, %3}, [%4];"
               : "=r"(r[0]), "=r"(r[1]), "=r"(r[2]), "=r"(r[3]) : "r"(a) : "memory");
}
__device__ __forceinline__ void ldsm4t(uint32_t* r, uint32_t a) {
  asm volatile("ldmatrix.sync.aligned.m8n8.x4.trans.shared.b16 {%0, %1, %2, %3}, [%4];"
               : "=r"(r[0]), "=r"(r[1]), "=r"(r[2]), "=r"(r[3]) : "r"(a) : "memory");
}
__device__ __forceinline__ uint2 lds64(uint32_t a) {
  uint2 v;
  asm volatile("ld.shared.v2.u32 {%0, %1}, [%2];" : "=r"(v.x), "=r"(v.y) : "r"(a) : "memory");
  return v;
}
__device__ __forceinline__ uint4 lds128(uint32_t a) {
  uint4 v;
  asm volatile("ld.shared.v4.u32 {%0, %1, %2, %3}, [%4];" : "=r"(v.x), "=r"(v.y), "=r"(v.z), "=r"(v.w) : "r"(a) : "memory");
  return v;
}
__device__ __forceinline__ void sts128(uint32_t a, uint32_t x, uint32_t y, uint32_t z, uint32_t w) {
  asm volatile("st.shared.v4.u32 [%0], {%1, %2, %3, %4};" ::"r"(a), "r"(x), "r"(y), "r"(z), "r"(w) : "memory");
}
__device__ __forceinline__ void stsm4(uint32_t a, const uint32_t* r) {
  asm volatile("stmatrix.sync.aligned.m8n8.x4.shared.b16 [%0], {%1, %2, %3, %4};" ::"r"(a), "r"(r[0]), "r"(r[1]), "r"(r[2]), "r"(r[3]) : "memory");
}
__device__ __forceinline__ uint32_t pack2(float lo, float hi) {
  uint32_t r;
  asm("cvt.rn.bf16x2.f32 %0, %1, %2;" : "=r"(r) : "f"(hi), "f"(lo));
  return r;
}
__device__ __forceinline__ uint32_t movm(uint32_t a) {
  uint32_t d;
  asm volatile("movmatrix.sync.aligned.m8n8.trans.b16 %0, %1;" : "=r"(d) : "r"(a));
  return d;
}
__device__ __forceinline__ uint32_t bmul(uint32_t a, uint32_t b) {
  uint32_t d;
  asm("mul.rn.bf16x2 %0, %1, %2;" : "=r"(d) : "r"(a), "r"(b));
  return d;
}
__device__ __forceinline__ uint32_t badd(uint32_t a, uint32_t b) {
  uint32_t d;
  asm("add.rn.bf16x2 %0, %1, %2;" : "=r"(d) : "r"(a), "r"(b));
  return d;
}
__device__ __forceinline__ uint32_t bfma(uint32_t a, uint32_t b, uint32_t c) {
  uint32_t d;
  asm("fma.rn.bf16x2 %0, %1, %2, %3;" : "=r"(d) : "r"(a), "r"(b), "r"(c));
  return d;
}
__device__ __forceinline__ float bf_lo(uint32_t x) { return __uint_as_float(x << 16); }
__device__ __forceinline__ float bf_hi(uint32_t x) { return __uint_as_float(x & 0xFFFF0000u); }
__device__ __forceinline__ float ex2(float x) {
  float y;
  asm("ex2.approx.ftz.f32 %0, %1;" : "=f"(y) : "f"(x));
  return y;
}
__device__ __forceinline__ float rcp(float x) {
  float y;
  asm("rcp.approx.ftz.f32 %0, %1;" : "=f"(y) : "f"(x));
  return y;
}
__device__ __forceinline__ void mma16816(float* d, uint32_t a0, uint32_t a1, uint32_t a2, uint32_t a3, uint32_t b0, uint32_t b1) {
  asm volatile("mma.sync.aligned.m16n8k16.row.col.f32.bf16.bf16.f32 {%0, %1, %2, %3}, {%4, %5, %6, %7}, {%8, %9}, {%0, %1, %2, %3};"
               : "+f"(d[0]), "+f"(d[1]), "+f"(d[2]), "+f"(d[3])
               : "r"(a0), "r"(a1), "r"(a2), "r"(a3), "r"(b0), "r"(b1));
}
__device__ __forceinline__ void mma1688(float* d, uint32_t a0, uint32_t a1, uint32_t b0) {
  asm volatile("mma.sync.aligned.m16n8k8.row.col.f32.bf16.bf16.f32 {%0, %1, %2, %3}, {%4, %5}, {%6}, {%0, %1, %2, %3};"
               : "+f"(d[0]), "+f"(d[1]), "+f"(d[2]), "+f"(d[3])
               : "r"(a0), "r"(a1), "r"(b0));
}

template <int N> struct WgRS;
template <int N> struct WgSST;
template <> struct WgRS<32> {
  template <uint32_t HB>
  static __device__ __forceinline__ void mma(float* d, const uint32_t* a, uint32_t db) {
    asm volatile("{\n.reg .pred p;\n.reg .b64 db;\nsetp.ne.b32 p, %22, 0;\n"
      "mov.b64 db, {%20, %21};\n"
      "wgmma.mma_async.sync.aligned.m64n32k16.f32.bf16.bf16 {"
      "%0, %1, %2, %3, %4, %5, %6, %7, %8, %9, %10, %11, %12, %13, %14, %15"
      "}, {%16, %17, %18, %19}, db, p, 1, 1, 1;\n}\n"
      : "+f"(d[0]), "+f"(d[1]), "+f"(d[2]), "+f"(d[3]), "+f"(d[4]), "+f"(d[5]), "+f"(d[6]), "+f"(d[7]),
        "+f"(d[8]), "+f"(d[9]), "+f"(d[10]), "+f"(d[11]), "+f"(d[12]), "+f"(d[13]), "+f"(d[14]), "+f"(d[15])
      : "r"(a[0]), "r"(a[1]), "r"(a[2]), "r"(a[3]), "r"(db), "n"(HB), "n"(1));
  }
  template <uint32_t HB>
  static __device__ __forceinline__ void set(float* d, const uint32_t* a, uint32_t db) {
    asm volatile("{\n.reg .pred p;\n.reg .b64 db;\nsetp.ne.b32 p, %22, 0;\n"
      "mov.b64 db, {%20, %21};\n"
      "wgmma.mma_async.sync.aligned.m64n32k16.f32.bf16.bf16 {"
      "%0, %1, %2, %3, %4, %5, %6, %7, %8, %9, %10, %11, %12, %13, %14, %15"
      "}, {%16, %17, %18, %19}, db, p, 1, 1, 1;\n}\n"
      : "=f"(d[0]), "=f"(d[1]), "=f"(d[2]), "=f"(d[3]), "=f"(d[4]), "=f"(d[5]), "=f"(d[6]), "=f"(d[7]),
        "=f"(d[8]), "=f"(d[9]), "=f"(d[10]), "=f"(d[11]), "=f"(d[12]), "=f"(d[13]), "=f"(d[14]), "=f"(d[15])
      : "r"(a[0]), "r"(a[1]), "r"(a[2]), "r"(a[3]), "r"(db), "n"(HB), "n"(0));
  }
};
template <> struct WgRS<64> {
  template <uint32_t HB>
  static __device__ __forceinline__ void mma(float* d, const uint32_t* a, uint32_t db) {
    asm volatile("{\n.reg .pred p;\n.reg .b64 db;\nsetp.ne.b32 p, %38, 0;\n"
      "mov.b64 db, {%36, %37};\n"
      "wgmma.mma_async.sync.aligned.m64n64k16.f32.bf16.bf16 {"
      "%0, %1, %2, %3, %4, %5, %6, %7, %8, %9, %10, %11, %12, %13, %14, %15, "
      "%16, %17, %18, %19, %20, %21, %22, %23, %24, %25, %26, %27, %28, %29, %30, %31"
      "}, {%32, %33, %34, %35}, db, p, 1, 1, 1;\n}\n"
      : "+f"(d[0]), "+f"(d[1]), "+f"(d[2]), "+f"(d[3]), "+f"(d[4]), "+f"(d[5]), "+f"(d[6]), "+f"(d[7]),
        "+f"(d[8]), "+f"(d[9]), "+f"(d[10]), "+f"(d[11]), "+f"(d[12]), "+f"(d[13]), "+f"(d[14]), "+f"(d[15]),
        "+f"(d[16]), "+f"(d[17]), "+f"(d[18]), "+f"(d[19]), "+f"(d[20]), "+f"(d[21]), "+f"(d[22]), "+f"(d[23]),
        "+f"(d[24]), "+f"(d[25]), "+f"(d[26]), "+f"(d[27]), "+f"(d[28]), "+f"(d[29]), "+f"(d[30]), "+f"(d[31])
      : "r"(a[0]), "r"(a[1]), "r"(a[2]), "r"(a[3]), "r"(db), "n"(HB), "n"(1));
  }
  template <uint32_t HB>
  static __device__ __forceinline__ void set(float* d, const uint32_t* a, uint32_t db) {
    asm volatile("{\n.reg .pred p;\n.reg .b64 db;\nsetp.ne.b32 p, %38, 0;\n"
      "mov.b64 db, {%36, %37};\n"
      "wgmma.mma_async.sync.aligned.m64n64k16.f32.bf16.bf16 {"
      "%0, %1, %2, %3, %4, %5, %6, %7, %8, %9, %10, %11, %12, %13, %14, %15, "
      "%16, %17, %18, %19, %20, %21, %22, %23, %24, %25, %26, %27, %28, %29, %30, %31"
      "}, {%32, %33, %34, %35}, db, p, 1, 1, 1;\n}\n"
      : "=f"(d[0]), "=f"(d[1]), "=f"(d[2]), "=f"(d[3]), "=f"(d[4]), "=f"(d[5]), "=f"(d[6]), "=f"(d[7]),
        "=f"(d[8]), "=f"(d[9]), "=f"(d[10]), "=f"(d[11]), "=f"(d[12]), "=f"(d[13]), "=f"(d[14]), "=f"(d[15]),
        "=f"(d[16]), "=f"(d[17]), "=f"(d[18]), "=f"(d[19]), "=f"(d[20]), "=f"(d[21]), "=f"(d[22]), "=f"(d[23]),
        "=f"(d[24]), "=f"(d[25]), "=f"(d[26]), "=f"(d[27]), "=f"(d[28]), "=f"(d[29]), "=f"(d[30]), "=f"(d[31])
      : "r"(a[0]), "r"(a[1]), "r"(a[2]), "r"(a[3]), "r"(db), "n"(HB), "n"(0));
  }
};
template <> struct WgSST<48> {
  template <uint32_t HA, uint32_t HB>
  static __device__ __forceinline__ void mma(float* d, uint32_t da, uint32_t db, int sc) {
    asm volatile("{\n.reg .pred p;\n.reg .b64 da, db;\nsetp.ne.b32 p, %28, 0;\n"
      "mov.b64 da, {%24, %25};\nmov.b64 db, {%26, %27};\n"
      "wgmma.mma_async.sync.aligned.m64n48k16.f32.bf16.bf16 {"
      "%0, %1, %2, %3, %4, %5, %6, %7, %8, %9, %10, %11, %12, %13, %14, %15, "
      "%16, %17, %18, %19, %20, %21, %22, %23"
      "}, da, db, p, 1, 1, 0, 1;\n}\n"
      : "+f"(d[0]), "+f"(d[1]), "+f"(d[2]), "+f"(d[3]), "+f"(d[4]), "+f"(d[5]), "+f"(d[6]), "+f"(d[7]),
        "+f"(d[8]), "+f"(d[9]), "+f"(d[10]), "+f"(d[11]), "+f"(d[12]), "+f"(d[13]), "+f"(d[14]), "+f"(d[15]),
        "+f"(d[16]), "+f"(d[17]), "+f"(d[18]), "+f"(d[19]), "+f"(d[20]), "+f"(d[21]), "+f"(d[22]), "+f"(d[23])
      : "r"(da), "n"(HA), "r"(db), "n"(HB), "r"(sc));
  }
};
template <> struct WgSST<80> {
  template <uint32_t HA, uint32_t HB>
  static __device__ __forceinline__ void mma(float* d, uint32_t da, uint32_t db, int sc) {
    asm volatile("{\n.reg .pred p;\n.reg .b64 da, db;\nsetp.ne.b32 p, %44, 0;\n"
      "mov.b64 da, {%40, %41};\nmov.b64 db, {%42, %43};\n"
      "wgmma.mma_async.sync.aligned.m64n80k16.f32.bf16.bf16 {"
      "%0, %1, %2, %3, %4, %5, %6, %7, %8, %9, %10, %11, %12, %13, %14, %15, "
      "%16, %17, %18, %19, %20, %21, %22, %23, %24, %25, %26, %27, %28, %29, %30, %31, "
      "%32, %33, %34, %35, %36, %37, %38, %39"
      "}, da, db, p, 1, 1, 0, 1;\n}\n"
      : "+f"(d[0]), "+f"(d[1]), "+f"(d[2]), "+f"(d[3]), "+f"(d[4]), "+f"(d[5]), "+f"(d[6]), "+f"(d[7]),
        "+f"(d[8]), "+f"(d[9]), "+f"(d[10]), "+f"(d[11]), "+f"(d[12]), "+f"(d[13]), "+f"(d[14]), "+f"(d[15]),
        "+f"(d[16]), "+f"(d[17]), "+f"(d[18]), "+f"(d[19]), "+f"(d[20]), "+f"(d[21]), "+f"(d[22]), "+f"(d[23]),
        "+f"(d[24]), "+f"(d[25]), "+f"(d[26]), "+f"(d[27]), "+f"(d[28]), "+f"(d[29]), "+f"(d[30]), "+f"(d[31]),
        "+f"(d[32]), "+f"(d[33]), "+f"(d[34]), "+f"(d[35]), "+f"(d[36]), "+f"(d[37]), "+f"(d[38]), "+f"(d[39])
      : "r"(da), "n"(HA), "r"(db), "n"(HB), "r"(sc));
  }
};
template <> struct WgSST<192> {
  template <uint32_t HA, uint32_t HB>
  static __device__ __forceinline__ void mma(float* d, uint32_t da, uint32_t db, int sc) {
    asm volatile("{\n.reg .pred p;\n.reg .b64 da, db;\nsetp.ne.b32 p, %100, 0;\n"
      "mov.b64 da, {%96, %97};\nmov.b64 db, {%98, %99};\n"
      "wgmma.mma_async.sync.aligned.m64n192k16.f32.bf16.bf16 {"
      "%0, %1, %2, %3, %4, %5, %6, %7, %8, %9, %10, %11, %12, %13, %14, %15, "
      "%16, %17, %18, %19, %20, %21, %22, %23, %24, %25, %26, %27, %28, %29, %30, %31, "
      "%32, %33, %34, %35, %36, %37, %38, %39, %40, %41, %42, %43, %44, %45, %46, %47, "
      "%48, %49, %50, %51, %52, %53, %54, %55, %56, %57, %58, %59, %60, %61, %62, %63, "
      "%64, %65, %66, %67, %68, %69, %70, %71, %72, %73, %74, %75, %76, %77, %78, %79, "
      "%80, %81, %82, %83, %84, %85, %86, %87, %88, %89, %90, %91, %92, %93, %94, %95"
      "}, da, db, p, 1, 1, 0, 1;\n}\n"
      : "+f"(d[0]), "+f"(d[1]), "+f"(d[2]), "+f"(d[3]), "+f"(d[4]), "+f"(d[5]), "+f"(d[6]), "+f"(d[7]),
        "+f"(d[8]), "+f"(d[9]), "+f"(d[10]), "+f"(d[11]), "+f"(d[12]), "+f"(d[13]), "+f"(d[14]), "+f"(d[15]),
        "+f"(d[16]), "+f"(d[17]), "+f"(d[18]), "+f"(d[19]), "+f"(d[20]), "+f"(d[21]), "+f"(d[22]), "+f"(d[23]),
        "+f"(d[24]), "+f"(d[25]), "+f"(d[26]), "+f"(d[27]), "+f"(d[28]), "+f"(d[29]), "+f"(d[30]), "+f"(d[31]),
        "+f"(d[32]), "+f"(d[33]), "+f"(d[34]), "+f"(d[35]), "+f"(d[36]), "+f"(d[37]), "+f"(d[38]), "+f"(d[39]),
        "+f"(d[40]), "+f"(d[41]), "+f"(d[42]), "+f"(d[43]), "+f"(d[44]), "+f"(d[45]), "+f"(d[46]), "+f"(d[47]),
        "+f"(d[48]), "+f"(d[49]), "+f"(d[50]), "+f"(d[51]), "+f"(d[52]), "+f"(d[53]), "+f"(d[54]), "+f"(d[55]),
        "+f"(d[56]), "+f"(d[57]), "+f"(d[58]), "+f"(d[59]), "+f"(d[60]), "+f"(d[61]), "+f"(d[62]), "+f"(d[63]),
        "+f"(d[64]), "+f"(d[65]), "+f"(d[66]), "+f"(d[67]), "+f"(d[68]), "+f"(d[69]), "+f"(d[70]), "+f"(d[71]),
        "+f"(d[72]), "+f"(d[73]), "+f"(d[74]), "+f"(d[75]), "+f"(d[76]), "+f"(d[77]), "+f"(d[78]), "+f"(d[79]),
        "+f"(d[80]), "+f"(d[81]), "+f"(d[82]), "+f"(d[83]), "+f"(d[84]), "+f"(d[85]), "+f"(d[86]), "+f"(d[87]),
        "+f"(d[88]), "+f"(d[89]), "+f"(d[90]), "+f"(d[91]), "+f"(d[92]), "+f"(d[93]), "+f"(d[94]), "+f"(d[95])
      : "r"(da), "n"(HA), "r"(db), "n"(HB), "r"(sc));
  }
};

struct FftConst {
  uint32_t f[2][4], fi[4][4];
  uint32_t ta[2][2], tb[2][2];
};
__device__ __forceinline__ void cis(int m, float scale, float& c, float& s) {
  const float a = (float)m * (-6.283185307179586f * scale);
  c = __cosf(a);
  s = __sinf(a);
}
__device__ __forceinline__ void fft_tables(uint32_t (&v)[12], int tw) {
  const int row = tw >> 2, ch = tw & 3;
#pragma unroll
  for (int i = 0; i < 4; i++) {
    float c[2], s[2], x[2];
#pragma unroll
    for (int e = 0; e < 2; e++) {
      cis((((32 * (8 * ch + 2 * i + e) + 15) * (4 * row - 63) + 2048) & 4095) - 2048, 1.f / 4096, c[e], s[e]);
      float gc, gs;
      cis((((row & 15) * (8 * (ch & 1) + 2 * i + e) + 8) & 15) - 8, 1.f / 16, gc, gs);
      x[e] = (row >> 4) == (ch >> 1) ? gc : (ch >> 1) ? gs : -gs;
    }
    v[i] = pack2(c[0] * 0.125f, c[1] * 0.125f);
    v[4 + i] = pack2(s[0] * 0.125f, s[1] * 0.125f);
    v[8 + i] = pack2(x[0], x[1]);
  }
#pragma unroll
  for (int i = 0; i < 12; i++) asm volatile("" : "+r"(v[i]));
}
__device__ __forceinline__ void fft_tables_store(const uint32_t (&v)[12], uint32_t sb, int tw) {
  const int row = tw >> 2;
  const uint32_t x = ((tw ^ (row >> 1)) & 3) << 4, a = sb + OFF_FT + (16 * (row >> 3) + (row & 7)) * 64 + x;
  sts128(a, v[0], v[1], v[2], v[3]);
  sts128(a + 512, v[4], v[5], v[6], v[7]);
  sts128(sb + OFF_GT + row * 64 + x, v[8], v[9], v[10], v[11]);
}
__device__ __forceinline__ void fft_twiddles(uint32_t (&v)[2], int tw) {
  float a[2], s[2];
#pragma unroll
  for (int i = 0; i < 2; i++) {
    float c;
    cis((2 * (2 * (tw & 3) + i) - 15) * (4 * (tw >> 2) - 63), 1.f / 4096, c, s[i]);
    a[i] = __fdividef(-s[i], 1.f + c);
  }
  v[0] = pack2(a[0], a[1]);
  v[1] = pack2(s[0], s[1]);
  asm volatile("" : "+r"(v[0]), "+r"(v[1]));
}
__device__ __forceinline__ void fft_matrices(FftConst& k, uint32_t sb, int w, int lane) {
  const uint32_t x = (lane >> 1) & 3;
  const uint2 t0 = lds64(sb + OFF_TT + 256 * w + 8 * lane), t1 = lds64(sb + OFF_TT + 256 * w + 8 * (lane ^ 3));
  k.ta[0][0] = t0.x;
  k.tb[0][0] = t0.y;
  k.ta[1][1] = __byte_perm(t1.x, 0, 0x1032);
  k.tb[1][1] = __byte_perm(t1.y, 0, 0x1032);
#pragma unroll
  for (int j = 0; j < 2; j++) {
    k.ta[1 - j][j] = k.ta[j][j] ^ 0x80008000u;
    k.tb[1 - j][j] = k.tb[j][j] ^ 0x80008000u;
    asm volatile("" : "+r"(k.ta[0][j]), "+r"(k.tb[0][j]), "+r"(k.ta[1][j]), "+r"(k.tb[1][j]));
  }
#pragma unroll
  for (int i = 0; i < 2; i++) {
    ldsm4(k.f[i], sb + OFF_FT + (16 * w + (lane & 15)) * 64 + (((2 * i + (lane >> 4)) ^ x) << 4));
    ldsm4t(k.fi[i], sb + OFF_FT + (32 * i + lane) * 64 + ((w ^ x) << 4));
#pragma unroll
    for (int j = 0; j < 4; j++) {
      k.fi[2 + i][j] = (j & 1) ? k.fi[i][j - 1] ^ 0x80008000u : k.fi[i][j + 1];
      asm volatile("" : "+r"(k.fi[2 + i][j]));
    }
  }
}
__device__ __forceinline__ void rot(uint32_t& x, uint32_t& y, uint32_t a, uint32_t b) {
  x = bfma(a, y, x);
  y = bfma(b, x, y);
  x = bfma(a, y, x);
}
__device__ __forceinline__ void twiddle_fwd(uint32_t (&a)[4][4], float* d, const FftConst& k) {
#pragma unroll
  for (int q = 0; q < 4; q++)
#pragma unroll
    for (int j = 0; j < 2; j++) {
      const float* x = d + 8 * q + 4 * j;
      uint32_t re = pack2(x[0], x[1]), im = pack2(x[2], x[3]);
      rot(re, im, k.ta[0][j], k.tb[0][j]);
      a[q & 2][2 * j + (q & 1)] = re;
      a[(q & 2) + 1][2 * j + (q & 1)] = im;
    }
}
__device__ __forceinline__ void g_step(float* d, const uint32_t (&a)[4][4], uint32_t dre, uint32_t dim) {
  WgRS<32>::set<HI_SW64>(d, a[0], dre);
  WgRS<32>::set<HI_SW64>(d + 16, a[2], dre);
  WgRS<32>::mma<HI_SW64>(d, a[1], dim);
  WgRS<32>::mma<HI_SW64>(d + 16, a[3], dim);
  wg_commit();
}

__device__ __forceinline__ void products(uint32_t (&a)[4][4], const float* H, const float* U, int p) {
#pragma unroll
  for (int j = 0; j < 2; j++)
#pragma unroll
    for (int m = 2 * p; m < 2 * p + 2; m++) {
      float pr[2], pi[2];
#pragma unroll
      for (int x = 0; x < 2; x++)
#pragma unroll
        for (int q = 0; q <= m; q++) {
          const int ih = 16 * (q >> 1) + 2 * (q & 1) + 4 * j + x, iu = 16 * ((m - q) >> 1) + 2 * ((m - q) & 1) + 4 * j + x;
          pr[x] = q ? fmaf(H[ih], U[iu], pr[x]) : H[ih] * U[iu];
          pi[x] = q ? fmaf(H[ih], U[iu + 8], pi[x]) : H[ih] * U[iu + 8];
          pr[x] = fmaf(-H[ih + 8], U[iu + 8], pr[x]);
          pi[x] = fmaf(H[ih + 8], U[iu], pi[x]);
        }
      a[m & 2][2 * j + (m & 1)] = pack2(pr[0], pr[1]);
      a[(m & 2) + 1][2 * j + (m & 1)] = pack2(pi[0], pi[1]);
    }
}

__device__ __forceinline__ void conv_channel(const FftConst& k, uint32_t sb, int c, int wg, int w, int lane) {
  const uint32_t cb = sb + off_ch(c), bars = sb + OFF_BAR;
  const uint32_t du = desc_lo(cb, 1024), dg = desc_lo(sb + OFF_GT, 16), dz = desc_lo(cb + U_BYTES, 16);
  float U[32], H[32];
  uint32_t a[4][4], e[4][4];
  const float dv = __uint_as_float(lds32(sb + OFF_D + 4 * c));
  wg_fence();
  WgRS<64>::set<HI_SW32>(H, k.f[0], du + 256);
  WgRS<64>::mma<HI_SW32>(H, k.f[1], du + 256 + 32);
  wg_commit();
  wg_wait<0>();
  pin<32>(H);
  twiddle_fwd(a, H, k);
  mbar_wait(bars + 8 * (B_U + (c < 3 ? c : 3)), 0);
  TSM(w == 0 && c < 3, 7 + wg);
  wg_fence();
  WgRS<64>::set<HI_SW32>(U, k.f[0], du);
  WgRS<64>::mma<HI_SW32>(U, k.f[1], du + 32);
  wg_commit();
  g_step(H, a, dg, dg + 64);
  wg_wait<1>();
  pin<32>(U);
  twiddle_fwd(e, U, k);
  wg_fence();
  g_step(U, e, dg, dg + 64);
  wg_wait<0>();
  pin<32>(U);
  pin<32>(H);
#pragma unroll
  for (int j = 0; j < 4; j++) H[4 * (j >> 1) + (j & 1)] += dv;
  float V[32];
#pragma unroll
  for (int p = 0; p < 2; p++) {
    products(a, H, U, p);
    wg_fence();
    WgRS<32>::set<HI_SW64>(V + 16 * p, a[2 * p], dg + 64);
    WgRS<32>::mma<HI_SW64>(V + 16 * p, a[2 * p + 1], dg);
    wg_commit();
  }
  const uint32_t za = cb + U_BYTES + (8 * w + (lane & 7)) * 128 + (((lane >> 3) ^ (lane & 7)) << 4);
  const uint32_t ya = cb + (lane >> 4) * 1024 + (8 * w + (lane & 7)) * 32 + ((((lane >> 3) ^ (lane >> 2)) & 1) << 4);
  wg_sync(1 + wg);
#pragma unroll
  for (int p = 0; p < 2; p++) {
    if (p == 0) wg_wait<1>();
    else wg_wait<0>();
    pin<16>(V + 16 * p);
#pragma unroll
    for (int i = 0; i < 4; i++) {
      const int j = i & 1;
      const float* x = V + 16 * p + 4 * j + (i & 2);
      e[p][i] = pack2(x[8], x[9]);
      e[2 + p][i] = pack2(x[0], x[1]);
      rot(e[p][i], e[2 + p][i], k.ta[1][j], k.tb[1][j]);
    }
    stsm4(za ^ (64 * p), e[p]);
    stsm4((za ^ (64 * p)) + 4096, e[2 + p]);
  }
  fence_async_smem();
  wg_sync(1 + wg);
  wg_fence();
  WgRS<64>::set<HI_SW128>(H, k.fi[0], dz);
#pragma unroll
  for (int ks = 1; ks < 4; ks++) WgRS<64>::mma<HI_SW128>(H, k.fi[ks], dz + 128 * ks);
  wg_commit();
  wg_wait<0>();
  pin<32>(H);
  if (lane == 0) mbar_arrive(bars + 8 * B_CVD);
  TSIF(w == 0, 88 + c);
#pragma unroll
  for (int j = 0; j < 8; j++)
    a[j >> 2][j & 3] = j < 2 ? pack2(H[4 * j], H[4 * j + 1]) : pack2(H[4 * j] + H[4 * j - 6], H[4 * j + 1] + H[4 * j - 5]);
  stsm4(ya, a[0]);
  stsm4(ya + 2048, a[1]);
  fence_async_smem();
  __syncwarp();
}

__device__ __forceinline__ void prep_slab(uint4* res, const uint2* sw, uint32_t sb, int slab, int w, int lane) {
  const int t = lane & 3, tp = (lane & 7) >> 1, pos = 8 * tp + 2 * (((lane >> 3) + tp) & 3) + (lane & 1);
  const uint32_t base = sb + OFF_KVS + slab * KVS_BYTES + pos * 128;
  uint32_t kk[2][4][4], vv[2][4];
  mbar_wait(sb + OFF_BAR + 8 * (B_KV + slab), 0);
#pragma unroll
  for (int h = 0; h < 2; h++) {
#pragma unroll
    for (int j = 0; j < 4; j++) {
      const uint32_t a = base + 128 * j;
      ldsm4t(kk[h][j], a + (((w + 4 * h) ^ ((a >> 7) & 7)) << 4));
    }
    const uint32_t a = base + KVS_V;
    ldsm4t(vv[h], a + (((w + 4 * h) ^ ((a >> 7) & 7)) << 4));
  }
#pragma unroll
  for (int h = 0; h < 2; h++) {
    uint32_t (&k)[4][4] = kk[h];
    uint32_t (&v)[4] = vv[h];
    const uint32_t w0 = __byte_perm(sw[h].x, 0, 0x1010), w1 = __byte_perm(sw[h].x, 0, 0x3232);
    const uint32_t w2 = __byte_perm(sw[h].y, 0, 0x1010), w3 = __byte_perm(sw[h].y, 0, 0x3232);
#pragma unroll
    for (int m = 0; m < 4; m++)
      v[m] = bmul(badd(badd(badd(bmul(k[0][m], w3), bmul(k[1][m], w2)), bmul(k[2][m], w1)), bmul(k[3][m], w0)), v[m]);
    uint32_t a[4];
#pragma unroll
    for (int m = 0; m < 4; m++) a[m] = (t & 1) ? v[(m + 3) & 3] : v[m];
    res[h] = (t & 2) ? make_uint4(a[2], a[3], a[0], a[1]) : make_uint4(a[0], a[1], a[2], a[3]);
  }
}

__device__ __forceinline__ void prep_gate(const Params& p, uint32_t sb, int b, int w, int lane) {
  uint2 gw[5], x[4][5];
#pragma unroll
  for (int j = 0; j < 5; j++) gw[j] = ldg64(reinterpret_cast<const uint2*>(p.gate_w) + lane + 32 * j);
#pragma unroll
  for (int i = 0; i < 4; i++)
#pragma unroll
    for (int j = 0; j < 5; j++)
      x[i][j] = ldg64(reinterpret_cast<const uint2*>(p.q) + (16 * b + 4 * w + i) * (DIM / 4) + lane + 32 * j);
  float s[4];
#pragma unroll
  for (int i = 0; i < 4; i++) {
    s[i] = 0.f;
#pragma unroll
    for (int j = 0; j < 5; j++) {
      const uint32_t m0 = bmul(x[i][j].x, gw[j].x), m1 = bmul(x[i][j].y, gw[j].y);
      s[i] += (bf_lo(m0) + bf_hi(m0)) + (bf_lo(m1) + bf_hi(m1));
    }
  }
  const bool h = lane & 16, q = lane & 8;
  const float a = (h ? s[2] : s[0]) + __shfl_xor_sync(0xffffffffu, h ? s[0] : s[2], 16);
  const float c = (h ? s[3] : s[1]) + __shfl_xor_sync(0xffffffffu, h ? s[1] : s[3], 16);
  float z = (q ? c : a) + __shfl_xor_sync(0xffffffffu, q ? a : c, 8);
#pragma unroll
  for (int o = 4; o > 0; o >>= 1) z += __shfl_xor_sync(0xffffffffu, z, o);
  z = bf_lo(pack2(z, 0.f));
  z = bf_lo(pack2(__fdividef(1.f, 1.f + __expf(-z)), 0.f));
  mbar_wait(sb + OFF_BAR + 8 * B_S3, 0);
  if ((lane & 7) == 0) asm volatile("st.shared.f32 [%0], %1;" ::"r"(sb + OFF_GATE + 64 * (b & 7) + 16 * w + (lane >> 1)), "f"(z) : "memory");
  fence_async_smem();
}

__device__ __forceinline__ uint32_t bmax(uint32_t a, uint32_t b) {
  uint32_t d;
  asm("max.bf16x2 %0, %1, %2;" : "=r"(d) : "r"(a), "r"(b));
  return d;
}
__device__ __forceinline__ void softmax_two(const float (&l)[2][2], uint32_t& p0, uint32_t& p1) {
  constexpr float kScale = 0.22360679774997896f, kLog2e = 1.4426950408889634f;
  const uint32_t r0 = pack2(l[0][0], l[1][0]), r1 = pack2(l[0][1], l[1][1]);
  const uint32_t x0 = pack2(bf_lo(r0) * kScale, bf_hi(r0) * kScale), x1 = pack2(bf_lo(r1) * kScale, bf_hi(r1) * kScale);
  uint32_t m = bmax(x0, x1);
  m = bmax(m, __shfl_xor_sync(0xffffffffu, m, 1));
  m = bmax(m, __shfl_xor_sync(0xffffffffu, m, 2));
  const float m0 = bf_lo(m) * kLog2e, m1 = bf_hi(m) * kLog2e;
  p0 = pack2(ex2(bf_lo(x0) * kLog2e - m0), ex2(bf_lo(x1) * kLog2e - m0));
  p1 = pack2(ex2(bf_hi(x0) * kLog2e - m1), ex2(bf_hi(x1) * kLog2e - m1));
}

__device__ __forceinline__ void halo_read(uint32_t (&kpv)[10], uint32_t (&vpv)[10], uint32_t (&tg)[7], const uint4* hp) {
#pragma unroll
  for (int j = 0; j < 7; j++) {
    uint32_t x0, x1, x2;
    asm volatile("ld.relaxed.gpu.global.v4.u32 {%0, %1, %2, %3}, [%4];"
                 : "=r"(x0), "=r"(x1), "=r"(x2), "=r"(tg[j]) : "l"(hp + 32 * j) : "memory");
    if (j < 4) kpv[3 * j] = x0; else vpv[3 * j - 10] = x0;
    if (j < 3) kpv[3 * j + 1] = x1; else vpv[3 * j - 9] = x1;
    if (j < 3) kpv[3 * j + 2] = x2; else if (j < 6) vpv[3 * j - 8] = x2;
  }
}

template <int ROT>
__device__ __forceinline__ void pack_qkv(const float* acc, uint32_t (&qlo)[10], uint32_t (&qhi)[10], uint32_t (&klo)[10],
                                         uint32_t (&khi)[10], uint32_t (&vlo)[10], uint32_t (&vhi)[10]) {
#pragma unroll
  for (int j = 0; j < 10; j++) {
    const int x = (j + ROT) % 10, tq = x < 8 ? x : 16 + x, tk = x < 8 ? 8 + x : 18 + x, tv = x < 8 ? 16 + x : 20 + x;
    khi[j] = pack2(acc[4 * tk + 2], acc[4 * tk + 3]);
    vhi[j] = movm(pack2(acc[4 * tv + 2], acc[4 * tv + 3]));
    qlo[j] = pack2(acc[4 * tq], acc[4 * tq + 1]);
    qhi[j] = pack2(acc[4 * tq + 2], acc[4 * tq + 3]);
    klo[j] = pack2(acc[4 * tk], acc[4 * tk + 1]);
    vlo[j] = pack2(acc[4 * tv], acc[4 * tv + 1]);
    asm volatile("" : "+r"(khi[j]), "+r"(qlo[j]), "+r"(qhi[j]), "+r"(klo[j]), "+r"(vlo[j]));
  }
}

template <int ROT> __device__ __forceinline__ void halo_send(const float* acc, uint4* ho, uint32_t tag) {
#pragma unroll
  for (int j = 0; j < 7; j++) {
    uint32_t x[3];
#pragma unroll
    for (int e = 0; e < 3; e++) {
      const int i = 3 * j + e, y = (i % 10 + ROT) % 10, tk = y < 8 ? 8 + y : 18 + y, tv = y < 8 ? 16 + y : 20 + y;
      x[e] = i < 10 ? pack2(acc[4 * tk + 2], acc[4 * tk + 3]) : i < 20 ? movm(pack2(acc[4 * tv + 2], acc[4 * tv + 3])) : 0u;
    }
    asm volatile("st.relaxed.gpu.global.v4.u32 [%0], {%1, %2, %3, %4};" ::"l"(ho + 32 * j), "r"(x[0]), "r"(x[1]), "r"(x[2]), "r"(tag) : "memory");
  }
}

__device__ __forceinline__ void attention(float* acc, uint32_t sb, int b, int par, int w, int lane, uint32_t tag) {
  const int g = lane >> 2, t = lane & 3;
  uint32_t klo[10], khi[10], vlo[10], vhi[10], qlo[10], qhi[10], kpv[10], vpv[10];
  if (w == 3 && b < NCTA - 8) {
    uint4* ho = g_halo + (b * 2 + par) * 224 + lane;
    if (tail_first(b & 7)) halo_send<8>(acc, ho, tag);
    else halo_send<0>(acc, ho, tag);
    TSIF(par == 0, 76);
    pin<120>(acc);
  }
  if (tail_first(b & 7)) pack_qkv<8>(acc, qlo, qhi, klo, khi, vlo, vhi);
  else pack_qkv<0>(acc, qlo, qhi, klo, khi, vlo, vhi);
  const uint32_t xa = sb + OFF_KVX + (par * 3) * 2560 + lane * 16;
  if (w < 3) {
    sts128(xa + w * 2560, khi[0], khi[1], khi[2], khi[3]);
    sts128(xa + w * 2560 + 512, khi[4], khi[5], khi[6], khi[7]);
    sts128(xa + w * 2560 + 1024, khi[8], khi[9], vhi[0], vhi[1]);
    sts128(xa + w * 2560 + 1536, vhi[2], vhi[3], vhi[4], vhi[5]);
    sts128(xa + w * 2560 + 2048, vhi[6], vhi[7], vhi[8], vhi[9]);
  }
  TSIF(par == 0 && w == 1, 64);
#pragma unroll
  for (int j = 0; j < 10; j++) vlo[j] = movm(vlo[j]);
  const bool far0 = 2 * t > g, far1 = 2 * t + 1 > g;
  const uint32_t mfar = (far0 ? 0x0000FFFFu : 0u) | (far1 ? 0xFFFF0000u : 0u);
  float slo[4][2], lg[2][2];
  uint32_t phi[4], plo[4], qml[4], qmh[4];
#pragma unroll
  for (int h = 0; h < 4; h++) {
    const int f = h == 0 ? 0 : h == 1 ? 3 : h == 2 ? 5 : 8, hf = h < 2 ? 2 : 7;
    const bool mine = (h & 1) ? t >= 2 : t < 2;
    qml[h] = mine ? qlo[hf] : 0u;
    qmh[h] = mine ? qhi[hf] : 0u;
    float a[4] = {0.f, 0.f, 0.f, 0.f}, c[4] = {0.f, 0.f, 0.f, 0.f};
    mma16816(a, qlo[f], qhi[f], qlo[f + 1], qhi[f + 1], klo[f], klo[f + 1]);
    mma16816(c, qlo[f], qhi[f], qlo[f + 1], qhi[f + 1], khi[f], khi[f + 1]);
    mma1688(a, qml[h], qmh[h], klo[hf]);
    mma1688(c, qml[h], qmh[h], khi[hf]);
    slo[h][0] = a[0];
    slo[h][1] = a[1];
    lg[h & 1][0] = far0 ? a[2] : c[2];
    lg[h & 1][1] = far1 ? a[3] : c[3];
    if (h & 1) softmax_two(lg, phi[h - 1], phi[h]);
  }
  TSIF(par == 0 && w == 1, 65);
  wg_sync(1 + par);
  TSIF(par == 0 && w == 1, 66);
  const bool nohist = (w == 0) && (b < 8);
  const uint4* hp = g_halo + ((b - 8) * 2 + par) * 224 + lane;
  uint32_t tg[7];
  if (w > 0) {
    const uint4 v0 = lds128(xa + (w - 1) * 2560), v1 = lds128(xa + (w - 1) * 2560 + 512), v2 = lds128(xa + (w - 1) * 2560 + 1024);
    const uint4 v3 = lds128(xa + (w - 1) * 2560 + 1536), v4 = lds128(xa + (w - 1) * 2560 + 2048);
    kpv[0] = v0.x; kpv[1] = v0.y; kpv[2] = v0.z; kpv[3] = v0.w; kpv[4] = v1.x; kpv[5] = v1.y; kpv[6] = v1.z; kpv[7] = v1.w;
    kpv[8] = v2.x; kpv[9] = v2.y; vpv[0] = v2.z; vpv[1] = v2.w; vpv[2] = v3.x; vpv[3] = v3.y; vpv[4] = v3.z; vpv[5] = v3.w;
    vpv[6] = v4.x; vpv[7] = v4.y; vpv[8] = v4.z; vpv[9] = v4.w;
  } else if (nohist) {
#pragma unroll
    for (int j = 0; j < 10; j++) kpv[j] = vpv[j] = 0u;
  } else {
    TSIF(par == 0, 77);
    halo_read(kpv, vpv, tg, hp);
  }
  if (w == 0 && !nohist) {
    int spins = 0;
    while (true) {
      bool ok = true;
#pragma unroll
      for (int j = 0; j < 7; j++) ok = ok && tg[j] == tag;
      if (__all_sync(0xffffffffu, ok) || ++spins > SPIN_LIMIT) break;
      halo_read(kpv, vpv, tg, hp);
    }
    TSIF(par == 0, 79);
  }
#pragma unroll
  for (int h = 0; h < 4; h++) {
    const int f = h == 0 ? 0 : h == 1 ? 3 : h == 2 ? 5 : 8, hf = h < 2 ? 2 : 7;
    float a[4] = {0.f, 0.f, 0.f, 0.f};
    mma16816(a, qlo[f], qhi[f], qlo[f + 1], qhi[f + 1], kpv[f], kpv[f + 1]);
    mma1688(a, qml[h], qmh[h], kpv[hf]);
    const float ninf = __int_as_float(0xff800000);
    lg[h & 1][0] = far0 ? (nohist ? ninf : a[0]) : slo[h][0];
    lg[h & 1][1] = far1 ? (nohist ? ninf : a[1]) : slo[h][1];
    if (h & 1) softmax_two(lg, plo[h - 1], plo[h]);
  }
  TSIF(par == 0 && w <= 1, 67 + w);
  uint32_t ov[20];
#pragma unroll
  for (int hp = 0; hp < 2; hp++) {
    const int hf = hp ? 7 : 2;
    float sh[4] = {0.f, 0.f, 0.f, 0.f}, i0 = 0.f, i1 = 0.f;
#pragma unroll
    for (int e = 0; e < 2; e++) {
      const int h = 2 * hp + e, f = h == 0 ? 0 : h == 1 ? 3 : h == 2 ? 5 : 8;
      const uint32_t a0 = plo[h] & mfar, a2 = plo[h] & ~mfar, a3 = phi[h] & mfar, c1 = phi[h] & ~mfar;
      float sum[4] = {0.f, 0.f, 0.f, 0.f};
      mma1688(sum, plo[h], phi[h], 0x3F803F80u);
      const float r0 = rcp(sum[0]), r1 = rcp(sum[2]);
#pragma unroll
      for (int j = f; j < f + 2; j++) {
        float o[4] = {0.f, 0.f, 0.f, 0.f};
        mma16816(o, a0, 0u, a2, a3, vpv[j], vlo[j]);
        mma1688(o, 0u, c1, vhi[j]);
        ov[2 * j] = pack2(o[0] * r0, o[1] * r0);
        ov[2 * j + 1] = pack2(o[2] * r1, o[3] * r1);
      }
      const bool mine = e ? g >= 4 : g < 4;
      mma16816(sh, a0, 0u, a2, a3, mine ? vpv[hf] : 0u, mine ? vlo[hf] : 0u);
      mma1688(sh, 0u, c1, mine ? vhi[hf] : 0u);
      if (e == 0 || t >= 2) {
        i0 = r0;
        i1 = r1;
      }
    }
    ov[2 * hf] = pack2(sh[0] * i0, sh[1] * i0);
    ov[2 * hf + 1] = pack2(sh[2] * i1, sh[3] * i1);
  }
  TS(32 + 4 * par + w);
  mbar_wait(sb + OFF_BAR + 8 * B_P1, 0);
  const uint32_t oa = sb + OFF_OA + (lane >> 4) * 2048 + (32 * w + 2 * (lane & 15) + par) * 16;
#pragma unroll
  for (int j = 0; j < 5; j++) stsm4(oa + 4096 * j, ov + 4 * j);
  TSIF(par == 0 && w == 0, 120);
  fence_async_smem();
  TSIF(par == 0 && w == 0, 121);
  __syncwarp();
  if (lane == 0) mbar_arrive(sb + OFF_BAR + 8 * B_ATTN);
  TSM(w == 0 || w == 2, 122 + par + (w == 2 ? 3 : 0));
}

struct Maps {
  CUtensorMap x, wm, wt, k, v, y, wo, qm, qt, om, ot;
};

__device__ __forceinline__ void load_stage(uint32_t sb, int kb, int b, const Maps& m) {
  const uint32_t st = sb + (kb & 3) * STAGE_BYTES, bar = sb + OFF_BAR + 8 * (B_FULL1 + (kb & 3));
  const int r = b >> 3, hg = b & 7, slab = kb - KV_KB;
  const bool kv = slab >= 0 && slab < 5;
  const uint32_t kbar = sb + OFF_BAR + 8 * (B_KV + slab), dst = sb + OFF_KVS + slab * KVS_BYTES;
  mbar_expect_tx(bar, STAGE_BYTES);
  if (kv) mbar_expect_tx(kbar, KVS_BYTES);
  tma_3d(st, &m.x, 64 * kb, 64 * r, 0, bar);
  tma_3d(st + ST_W, &m.wm, 80 * hg + (tail_first(hg) ? 16 : 0), 64 * kb, 0, bar);
  tma_3d(st + ST_WT, &m.wt, 80 * hg + (tail_first(hg) ? 0 : 64), 64 * kb, 0, bar);
  if (kv) tma_3d(dst, &m.k, 0, 32 * (b >> 1) - 3, 2 * slab + (b & 1), kbar);
  if (kv) tma_3d(dst + KVS_V, &m.v, 0, 32 * (b >> 1), 2 * slab + (b & 1), kbar);
}

__global__ void __launch_bounds__(NTHR, 1) fused_kernel(const __grid_constant__ Maps m, const Params p) {
  extern __shared__ __align__(1024) uint8_t smem[];
  const uint32_t sb = (uint32_t)__cvta_generic_to_shared(smem);
  const uint32_t bars = sb + OFF_BAR;
  const int tid = threadIdx.x, lane = tid & 31;
  int b = blockIdx.x;
  b = (((b & 63) >> 3) * 2 + (b & 1)) * 8 + (((b < 64 ? 0x6521 : 0x7430) >> (4 * ((b >> 1) & 3))) & 7);
  const int r = b >> 3, hg = b & 7;

  if (tid == T_ISSUE) {
    TSM(true, 0);
    mbar_init(bars + 8 * B_F0, 1);
    fence_async_smem();
    mbar_expect_tx(bars + 8 * B_F0, ST_WT);
    tma_3d(sb, &m.x, 0, 64 * r, 0, bars + 8 * B_F0);
    tma_3d(sb + ST_W, &m.wm, 80 * hg + (tail_first(hg) ? 16 : 0), 0, 0, bars + 8 * B_F0);
#pragma unroll
    for (int i = 0; i < 4; i++) mbar_init(bars + 8 * (B_FULL1 + i), 1);
    fence_async_smem();
    mbar_expect_tx(bars + 8 * B_FULL1, STAGE_BYTES - ST_WT);
    tma_3d(sb + ST_WT, &m.wt, 80 * hg + (tail_first(hg) ? 0 : 64), 0, 0, bars + 8 * B_FULL1);
    load_stage(sb, 1, b, m);
  } else if (tid == T_INIT) {
#pragma unroll
    for (int i = 0; i < B_F0; i++) mbar_init(bars + 8 * i, i < B_GATE ? 8 : i < B_CVD ? 4 : i == B_CVD ? 20 : 1);
    fence_async_smem();
  }
  const int warp = __shfl_sync(0xffffffffu, tid >> 5, 0), wg = warp >> 2, w = warp & 3;
  __syncthreads();

  if (wg == 3) {
    asm volatile("setmaxnreg.dec.sync.aligned.u32 56;");
    if (w == 0) {
      if (lane == 0) {
#pragma unroll 1
        for (int kb = 2; kb < 10; kb++) {
          if (kb >= 4) mbar_wait(bars + 8 * (kb == 7 ? B_E3 : B_EMPTY1 + (kb & 3)), (kb >> 3) & 1);
          TSIF(kb >= 4, 44 + kb);
          load_stage(sb, kb, b, m);
          TSIF(kb == 3, 60);
          if (kb == TRIG_KB) mbar_arrive(bars + 8 * B_LAST);
        }
        mbar_wait(bars + 8 * B_WOP, 0);
        mbar_wait(bars + 8 * WL_TRIG, 0);
        mbar_wait(bars + 8 * B_EPOCH, 0);
        flag_wait(g_cnt + C_W + 32 * hg, (lds32(sb + OFF_EPOCH) + 1) * 16);
        TS(30);
#pragma unroll 1
        for (int j = 0; j < 8; j++) {
          if (j >= 6) mbar_wait(bars + 8 * (B_EMPTY2 + j - 6), 0);
          if (j == 4) mbar_wait(bars + 8 * B_ATTN, 0);
          TSIF(j >= 6, 100 + j);
          mbar_expect_tx(bars + 8 * (B_FULL2 + j), j == 0 ? WO_BYTES : j == 5 ? O_BYTES + WO_BYTES + 512 : O_BYTES + WO_BYTES);
          bulk_load(sb + off_w(j), g_WO + (hg * 8 + step_src(hg, j)) * 800, WO_BYTES, bars + 8 * (B_FULL2 + j));
        }
        mbar_wait(bars + 8 * (B_EMPTY2 + 3), 0);
        mbar_expect_tx(bars + 8 * B_QF, O_BYTES);
        tma_2d(sb + OFF_QS, &m.qm, 80 * hg, 128 * r, bars + 8 * B_QF);
        tma_2d(sb + OFF_QT, &m.qt, 80 * hg + 64, 128 * r, bars + 8 * B_QF);
      }
    } else if (w == 1) {
      unsigned epoch = 0;
      if (lane == 0) {
        epoch = atomicAdd(g_cnt + C_LAUNCH, 1u) / NCTA;
        asm volatile("st.shared.u32 [%0], %1;" ::"r"(sb + OFF_EPOCH), "r"(epoch) : "memory");
        mbar_arrive(bars + 8 * B_EPOCH);
        mbar_wait(bars + 8 * B_KVD, 0);
        mbar_expect_tx(bars + 8 * B_HB, 5 * 4096);
#pragma unroll 1
        for (int c = 0; c < 5; c++) {
          if (c == 3) mbar_wait(bars + 8 * B_S3, 0);
          bulk_load(sb + off_ch(c) + U_BYTES, p.ssm_k + (5 * b + c) * SEQ, 4096, bars + 8 * B_HB);
        }
#pragma unroll
        for (int c = 0; c < 4; c++) mbar_expect_tx(bars + 8 * (B_U + c), c < 3 ? U_BYTES : 2 * U_BYTES);
        const uint4* usrc = g_U + 5 * b * U_PITCH;
        mbar_wait(bars + 8 * B_USIG, 0);
        flag_wait(g_cnt + C_PREP + 32 * (b & 15), (epoch + 1) * NCTA);
        TS(23);
#pragma unroll
        for (int c = 0; c < 5; c++) {
          if (c == 3) mbar_wait(bars + 8 * (B_U + 2), 0);
          bulk_load(sb + off_ch(c), usrc + c * U_PITCH, U_BYTES, bars + 8 * (B_U + (c < 3 ? c : 3)));
          TSIF(c == 0 || c == 4, 116 + (c >> 2));
        }
      }
      epoch = __shfl_sync(0xffffffffu, epoch, 0);
      if (lane < 8) {
        const int src = (b & ~7) | step_src(hg, lane);
        mbar_wait(bars + 8 * B_ATTN, 0);
        TS(20);
        const uint32_t slot = bars + 8 * (lane < 4 ? B_ATTN : lane < 6 ? B_C34 : B_EMPTY2 + lane - 6);
        bool seen = false, done = lane == 0, gate = false;
#pragma unroll 1
        for (int spins = 0; spins < SPIN_LIMIT; spins++) {
          if (!seen) seen = (int)(flag_read(g_cnt + C_O + 32 * src) - (epoch + 1)) >= 0;
          if (seen && !done && mbar_test(slot)) {
            bulk_load(sb + off_o(lane), g_O + src * 1280, O_BYTES, bars + 8 * (B_FULL2 + lane));
            done = true;
          }
          if (!gate && __all_sync(0xff, seen)) {
            gate = true;
            TS(21);
            if (lane == 5) bulk_load(sb + OFF_GATE, g_gate + 128 * r, 512, bars + 8 * (B_FULL2 + 5));
          }
          if (gate && __all_sync(0xff, done)) break;
        }
        TS(22);
      }
    } else if (w == 2) {
      mbar_wait(bars + 8 * B_PREP, 0);
      flag_signal(g_cnt + C_PREP, 16, lane);
      TS(25);
      if (lane == 0) {
        mbar_arrive(bars + 8 * B_USIG);
        mbar_expect_tx(bars + 8 * B_ORB, O_BYTES + 64);
        mbar_wait(bars + 8 * B_GATE, 0);
        publish(g_gate + 16 * b, sb + OFF_GATE + 64 * hg, 64, bars + 8 * B_ORB);
        mbar_wait(bars + 8 * B_ATTN, 0);
        publish(g_O + b * 1280, sb + OFF_OA, O_BYTES, bars + 8 * B_ORB);
        TS(74);
        mbar_wait(bars + 8 * B_ORB, 0);
        flag_bump(g_cnt + C_O + 32 * b);
        TS(26);
        mbar_arrive(bars + 8 * B_OSIG);
      }
    } else {
      if (lane == 0) {
        uint4* dst = g_WO + (hg * 8 + (r >> 1)) * 800 + (r & 1) * 80;
        mbar_wait(bars + 8 * B_S3, 0);
        asm volatile("cp.async.bulk.prefetch.L2.global [%0], 6400;" ::"l"(p.wo + b * 3200) : "memory");
        mbar_wait(bars + 8 * B_P1, 0);
        mbar_wait(bars + 8 * WB_TRIG, 0);
        mbar_expect_tx(bars + 8 * B_WST, WO_BYTES / 2);
        tma_3d(sb + OFF_WA, &m.wo, 0, 40 * r, 5 * hg, bars + 8 * B_WST);
        mbar_wait(bars + 8 * B_WST, 0);
#pragma unroll 1
        for (int n = 0; n < 5; n++) bulk_store(dst + 160 * n, sb + OFF_WA + 1280 * n, 1280);
        bulk_wait_read();
        mbar_expect_tx(bars + 8 * B_WST, WO_BYTES / 2);
#pragma unroll 1
        for (int n = 0; n < 5; n++) bulk_load(sb + OFF_WA + 1280 * n, dst + 160 * n, 1280, bars + 8 * B_WST);
        mbar_wait(bars + 8 * B_WST, 1);
        flag_bump(g_cnt + C_W + 32 * hg);
        mbar_arrive(bars + 8 * B_WOP);
        TS(71);
        mbar_expect_tx(bars + 8 * B_C34, 3 * U_BYTES);
        mbar_expect_tx(bars + 8 * B_YRB, 2 * U_BYTES);
#pragma unroll 1
        for (int c = 0; c < 5; c++) {
          mbar_wait(bars + 8 * (B_YST + c), 0);
          publish(g_U + (5 * b + c) * U_PITCH, sb + off_ch(c), U_BYTES, bars + 8 * (c < 3 ? B_C34 : B_YRB));
        }
        TS(75);
        mbar_wait(bars + 8 * B_C34, 0);
        mbar_wait(bars + 8 * B_YRB, 0);
        flag_bump(g_cnt + C_Y + 32 * (b >> 4));
        TS(27);
        mbar_arrive(bars + 8 * B_YSIG);
        mbar_expect_tx(bars + 8 * B_YFULL, 20480);
        flag_wait(g_cnt + C_Y + 32 * hg, (lds32(sb + OFF_EPOCH) + 1) * 16);
        TS(24);
        tma_2d(sb + OFF_YT, &m.y, 128 * r, 80 * hg, bars + 8 * B_YFULL);
        tma_2d(sb + OFF_YT + 10240, &m.y, 128 * r + 64, 80 * hg, bars + 8 * B_YFULL);
      }
    }
  } else {
    asm volatile("setmaxnreg.inc.sync.aligned.u32 152;");
    if (wg < 2) {
      float acc[120];
#pragma unroll
      for (int i = 0; i < 120; i++) acc[i] = 0.f;
      const uint32_t da = desc_lo(sb + wg * 8192, 16), db = desc_lo(sb + ST_W, 8192), dc = desc_lo(sb + ST_WT, 2048);
      mbar_wait(bars + 8 * B_F0, 0);
      TSIF(w == 0 && wg == 0, 1);
      wg_fence();
#pragma unroll
      for (int k = 0; k < 4; k++) WgSST<192>::mma<HI_SW128, HI_SW128>(acc, da + 2 * k, db + 128 * k, 1);
      wg_commit();
      mbar_wait(bars + 8 * B_FULL1, 0);
      wg_fence();
#pragma unroll
      for (int k = 0; k < 4; k++) WgSST<48>::mma<HI_SW128, HI_SW32>(acc + 96, da + 2 * k, dc + 32 * k, 1);
      wg_commit();
#pragma unroll 1
      for (int kb = 1; kb < 10; kb++) {
        mbar_wait(bars + 8 * (B_FULL1 + (kb & 3)), (kb >> 2) & 1);
        const uint32_t so = (kb & 3) * (STAGE_BYTES >> 4);
        wg_fence();
#pragma unroll
        for (int k = 0; k < 4; k++) {
          WgSST<192>::mma<HI_SW128, HI_SW128>(acc, da + so + 2 * k, db + so + 128 * k, 1);
          WgSST<48>::mma<HI_SW128, HI_SW32>(acc + 96, da + so + 2 * k, dc + so + 32 * k, 1);
        }
        wg_commit();
        wg_wait<1>();
        if (lane == 0) mbar_arrive(bars + 8 * (kb == 4 ? B_E3 : B_EMPTY1 + ((kb - 1) & 3)));
      }
      mbar_wait(bars + 8 * B_EPOCH, 0);
      const uint32_t tag = lds32(sb + OFF_EPOCH) + 1;
      mbar_wait(bars + 8 * B_S3, 0);
      wg_wait<0>();
      pin<120>(acc);
      if (lane == 0) mbar_arrive(bars + 8 * B_P1);
      TSM(w == 0, 3 + wg);
      attention(acc, sb, b, wg, w, lane, tag);
    } else {
      const int tw = tid & 127, chl = 64 * (b & 1) + 8 * w + (lane >> 2);
      uint4* up = g_U + chl * U_PITCH + ((4 * (b >> 1) + (lane & 3)) ^ ((b >> 2) & 1));
      uint2 sw[10];
      uint32_t dv = 0;
      if (lane < 5) dv = __ldg(reinterpret_cast<const unsigned short*>(p.ssm_D) + 5 * b + lane);
#pragma unroll
      for (int i = 0; i < 10; i++) sw[i] = ldg64(reinterpret_cast<const uint2*>(p.shift_k) + chl + 128 * (i >> 1) + 32 * (i & 1));
      uint32_t tab[12];
      uint32_t tt[2];
      fft_tables(tab, tw);
      fft_twiddles(tt, tw);
      uint4 res[10];
#pragma unroll
      for (int i = 0; i < 10; i++) res[i] = make_uint4(0, 0, 0, 0);
#pragma unroll 1
      for (int slab = 0; slab < 5; slab++) {
#pragma unroll
        for (int i = 0; i < 8; i++) res[i] = res[i + 2];
        prep_slab(res + 8, sw, sb, slab, w, lane);
        TSIF(w == 0, 99 + 4 * slab);
#pragma unroll
        for (int i = 0; i < 8; i++) sw[i] = sw[i + 2];
      }
      TSIF(w == 0, 28);
      __syncwarp();
      if (lane == 0) mbar_arrive(bars + 8 * B_KVD + ((res[8].x ^ res[9].x) & p.zero));
      mbar_wait(bars + 8 * B_KVD, 0);
      fft_tables_store(tab, sb, tw);
      mbar_wait(bars + 8 * B_LAST, 0);
#pragma unroll
      for (int i = 0; i < 10; i++) up[(128 * (i >> 1) + 32 * (i & 1)) * U_PITCH] = res[i];
      __syncwarp();
      if (lane == 0) mbar_arrive(bars + 8 * B_PREP);
      TSIF(w == 0, 5);
      mbar_wait(bars + 8 * B_LAST, 0);
      prep_gate(p, sb, b, w, lane);
      __syncwarp();
      if (lane == 0) mbar_arrive(bars + 8 * B_GATE);
      TSIF(w == 0, 72);
      mbar_wait(bars + 8 * B_HB, 0);
      TSIF(w == 0, 2);
      const uint32_t ha = sb + U_BYTES + ((tw >> 3) * 16 + 8 + (tw & 7)) * 16;
      uint4 hv[5];
#pragma unroll
      for (int c = 0; c < 5; c++) hv[c] = lds128(ha + off_ch(c));
      __syncwarp();
#pragma unroll
      for (int c = 0; c < 5; c++) sts128((ha ^ 16) + off_ch(c), hv[c].x, hv[c].y, hv[c].z, hv[c].w);
      asm volatile("st.shared.v2.u32 [%0], {%1, %2};" ::"r"(sb + OFF_TT + 8 * tw), "r"(tt[0]), "r"(tt[1]) : "memory");
      if (tw < 5) asm volatile("st.shared.f32 [%0], %1;" ::"r"(sb + OFF_D + 4 * tw), "f"(bf_lo(dv) * 0.125f) : "memory");
      fence_async_smem();
      __syncwarp();
      if (lane == 0) mbar_arrive(bars + 8 * B_HA);
      TSIF(w == 0, 6);
    }

    FftConst fc;
    TSM(w == 0 && wg == 0, 104);
    mbar_wait(bars + 8 * B_HA, 0);
    fft_matrices(fc, sb, w, lane);
    TSM(w == 0 && wg == 0, 105);
    TSM(w == 0 && wg == 2, 124);
#pragma unroll 1
    for (uint32_t tasks = wg == 0 ? TASK0 : wg == 1 ? TASK1 : TASK2; tasks; tasks >>= 4) {
      const int c = (tasks & 7) - 1;
      conv_channel(fc, sb, c, wg, w, lane);
      if (lane == 0) mbar_arrive(bars + 8 * (B_YST + c));
      TSM(w == 0, 10 + c);
    }

    if (wg < 2) {
      const int g = lane >> 2;
      float acc[40];
#pragma unroll
      for (int i = 0; i < 40; i++) acc[i] = 0.f;
      const uint32_t da = desc_lo(sb + wg * 1024, 2048), db = desc_lo(sb, 2560);
      mbar_wait(bars + 8 * B_ORB, 0);
      mbar_wait(bars + 8 * B_FULL2, 0);
      mbar_wait(bars + 8 * B_CVD, 0);
      TSM(w == 0, 15 + wg);
#pragma unroll 1
      for (int j = 0; j < 8; j++) {
        mbar_wait(bars + 8 * (B_FULL2 + j), 0);
        TSM(w == 0 && wg == 0, 44 + (j < 4 ? j : j + 6));
        const uint32_t oa = da + (off_o(j) >> 4), ob = db + (off_w(j) >> 4);
        wg_fence();
#pragma unroll
        for (int k = 0; k < 5; k++) WgSST<80>::mma<HI_NONE, HI_SW32>(acc, oa + 256 * k, ob + 32 * k, 1);
        wg_commit();
        wg_wait<1>();
        if (j >= 1 && j <= 4 && lane == 0) mbar_arrive(bars + 8 * (B_EMPTY2 + j - 1));
      }
      TSIF(w == 0 && wg == 0, 113);
      const int tr = 64 * wg + 16 * w + (lane & 15);
      const uint32_t fm = sb + OFF_QS + tr * 128, fx = (lane >> 4) ^ (tr & 7);
      const uint32_t ft = sb + OFF_QT + tr * 32 + (((lane >> 4) ^ (tr >> 2)) & 1) * 16;
      const float g0 = __uint_as_float(lds32(sb + OFF_GATE + (64 * wg + 16 * w + g) * 4));
      const float g1 = __uint_as_float(lds32(sb + OFF_GATE + (64 * wg + 16 * w + 8 + g) * 4));
      const uint32_t ga = pack2(g0, g0), gb = pack2(g1, g1);
      const uint32_t na = pack2(1.f - g0, 1.f - g0), nb = pack2(1.f - g1, 1.f - g1);

      uint32_t qf[20];
      mbar_wait(bars + 8 * B_QF, 0);
      TSM(w == 0 && wg == 0, 99);
#pragma unroll
      for (int j = 0; j < 5; j++) ldsm4(qf + 4 * j, j < 4 ? fm + ((fx ^ (2 * j)) << 4) : ft);
#pragma unroll
      for (int i = 0; i < 20; i++) {
        qf[i] = bmul((i & 1) ? gb : ga, qf[i]);
        asm volatile("" : "+r"(qf[i]));
      }

      wg_wait<0>();
      pin<40>(acc);
      TSM(w == 0, 17 + wg);
      uint32_t pb[20];
#pragma unroll
      for (int j = 0; j < 10; j++) {
        pb[2 * j] = bmul(na, pack2(acc[4 * j], acc[4 * j + 1]));
        pb[2 * j + 1] = bmul(nb, pack2(acc[4 * j + 2], acc[4 * j + 3]));
        asm volatile("" : "+r"(pb[2 * j]), "+r"(pb[2 * j + 1]));
      }
      const uint32_t ya = sb + OFF_YT + wg * 10240 + ((lane >> 4) * 8 + (lane & 7)) * 128 +
                          (((2 * w + (((lane >> 3) & 1) ^ wg)) ^ (lane & 7)) << 4);
      mbar_wait(bars + 8 * B_YFULL, 0);
      TSM(w == 0 && wg == 0, 19);
#pragma unroll
      for (int j = 0; j < 5; j++) {
        uint32_t y[4];
        ldsm4t(y, ya + 2048 * j);
#pragma unroll
        for (int i = 0; i < 4; i++)
          qf[4 * j + i] = bfma(qf[4 * j + i], y[i], pb[4 * j + i]);
      }
#pragma unroll
      for (int j = 0; j < 5; j++) stsm4(j < 4 ? fm + ((fx ^ (2 * j)) << 4) : ft, qf + 4 * j);
      fence_async_smem();
      __syncwarp();
      if (lane == 0) {
        const int row = 64 * wg + 16 * w;
        asm volatile("cp.async.bulk.tensor.2d.global.shared::cta.bulk_group [%0, {%2, %3}], [%1];"
                     ::"l"(&m.om), "r"(sb + OFF_QS + row * 128), "r"(80 * hg), "r"(128 * r + row) : "memory");
        asm volatile("cp.async.bulk.tensor.2d.global.shared::cta.bulk_group [%0, {%2, %3}], [%1];"
                     ::"l"(&m.ot), "r"(sb + OFF_QT + row * 32), "r"(80 * hg + 64), "r"(128 * r + row) : "memory");
        asm volatile("cp.async.bulk.commit_group;\ncp.async.bulk.wait_group.read 0;" ::: "memory");
      }
      TSM(w == 0 || w == 3, 40 + 2 * wg + (w & 1));
    }
  }
}

typedef CUresult (*EncodeFn)(CUtensorMap*, CUtensorMapDataType, cuuint32_t, void*, const cuuint64_t*, const cuuint64_t*,
                             const cuuint32_t*, const cuuint32_t*, CUtensorMapInterleave, CUtensorMapSwizzle,
                             CUtensorMapL2promotion, CUtensorMapFloatOOBfill);

void encode(EncodeFn fn, CUtensorMap* tm, const void* base, int rank, const cuuint64_t* dims, const cuuint64_t* strides,
            const cuuint32_t* box, CUtensorMapSwizzle swz) {
  const cuuint32_t ones[3] = {1, 1, 1};
  fn(tm, CU_TENSOR_MAP_DATA_TYPE_BFLOAT16, rank, const_cast<void*>(base), dims, strides, box, ones,
     CU_TENSOR_MAP_INTERLEAVE_NONE, swz, CU_TENSOR_MAP_L2_PROMOTION_L2_128B, CU_TENSOR_MAP_FLOAT_OOB_FILL_NONE);
}

}

extern "C" void kernel_launch(void* const* d_in, const int* in_sizes, int n_in, void* d_out, int out_size) {
  (void)in_sizes; (void)n_in; (void)out_size;
  Params p;
  p.q = (const __nv_bfloat16*)d_in[0];
  p.k = (const __nv_bfloat16*)d_in[1];
  p.v = (const __nv_bfloat16*)d_in[2];
  p.shift_k = (const __nv_bfloat16*)d_in[3];
  p.ssm_k = (const __nv_bfloat16*)d_in[4];
  p.ssm_D = (const __nv_bfloat16*)d_in[5];
  p.wqkv = (const __nv_bfloat16*)d_in[7];
  p.wo = (const __nv_bfloat16*)d_in[8];
  p.gate_w = (const __nv_bfloat16*)d_in[9];
  p.out = (__nv_bfloat16*)d_out;
  p.zero = 0;

  static EncodeFn fn = nullptr;
  static void* yaddr = nullptr;
  if (!fn) {
    cudaDriverEntryPointQueryResult qr;
    void* f = nullptr;
    cudaGetDriverEntryPoint("cuTensorMapEncodeTiled", &f, cudaEnableDefault, &qr);
    fn = (EncodeFn)f;
    cudaGetSymbolAddress(&yaddr, g_U);
    cudaFuncSetAttribute(fused_kernel, cudaFuncAttributeMaxDynamicSharedMemorySize, SMEM_BYTES);
  }
  Maps m;
  {
    const cuuint64_t dims[3] = {640, 1024, 2}, st[2] = {2560, 1280};
    const cuuint32_t box[3] = {64, 64, 2};
    encode(fn, &m.x, p.q, 3, dims, st, box, CU_TENSOR_MAP_SWIZZLE_128B);
  }
  {
    const cuuint64_t dims[3] = {640, 640, 3}, st[2] = {3840, 1280};
    const cuuint32_t box[3] = {64, 64, 3}, boxt[3] = {16, 64, 3};
    encode(fn, &m.wm, p.wqkv, 3, dims, st, box, CU_TENSOR_MAP_SWIZZLE_128B);
    encode(fn, &m.wt, p.wqkv, 3, dims, st, boxt, CU_TENSOR_MAP_SWIZZLE_32B);
  }
  {
    const cuuint64_t dims[3] = {64, 2048, 10}, st[2] = {1280, 128};
    const cuuint32_t boxk[3] = {64, 35, 1}, boxv[3] = {64, 32, 1};
    encode(fn, &m.k, p.k, 3, dims, st, boxk, CU_TENSOR_MAP_SWIZZLE_128B);
    encode(fn, &m.v, p.v, 3, dims, st, boxv, CU_TENSOR_MAP_SWIZZLE_128B);
  }
  {
    const cuuint64_t dims[3] = {16, 640, 40}, st[2] = {1280, 32};
    const cuuint32_t box[3] = {16, 40, 5};
    encode(fn, &m.wo, p.wo, 3, dims, st, box, CU_TENSOR_MAP_SWIZZLE_32B);
  }
  {
    const cuuint64_t dims[2] = {2048, 640}, st[1] = {U_PITCH * 16};
    const cuuint32_t box[2] = {64, 80};
    encode(fn, &m.y, yaddr, 2, dims, st, box, CU_TENSOR_MAP_SWIZZLE_128B);
  }
  {
    const cuuint64_t dims[2] = {640, 2048}, st[1] = {1280};
    const cuuint32_t bqm[2] = {64, 128}, bqt[2] = {16, 128}, bom[2] = {64, 16}, bot[2] = {16, 16};
    encode(fn, &m.qm, p.q, 2, dims, st, bqm, CU_TENSOR_MAP_SWIZZLE_128B);
    encode(fn, &m.qt, p.q, 2, dims, st, bqt, CU_TENSOR_MAP_SWIZZLE_32B);
    encode(fn, &m.om, p.out, 2, dims, st, bom, CU_TENSOR_MAP_SWIZZLE_128B);
    encode(fn, &m.ot, p.out, 2, dims, st, bot, CU_TENSOR_MAP_SWIZZLE_32B);
  }
  fused_kernel<<<NCTA, NTHR, SMEM_BYTES>>>(m, p);
}
```

```cpp
#include <cuda.h>
#include <cuda_bf16.h>
#include <cuda_runtime.h>
#include <stdint.h>

namespace {

constexpr int SEQ = 2048, DIM = 640, NCTA = 128, NTHR = 512;

#define TRIG_KB 9
#define KV_KB 2
#define DEV_EXIT 0
#define FENCE_LO 0
#define FENCE_HI 0
#define WB_TRIG B_USIG
#define T_ISSUE 256
#define RB32 3
#define T_INIT 448
#define TASK0 0x3
#define TASK1 0x52
#define TASK2 0x41
#define WL_TRIG B_WOP

constexpr uint32_t STAGE_BYTES = 47104, ST_W = 16384, ST_WT = 40960;
constexpr uint32_t O_BYTES = 20480, WO_BYTES = 12800;
constexpr uint32_t OFF_OA = 0;
constexpr uint32_t OFF_QS = 3 * O_BYTES, OFF_QT = OFF_QS + 16384;
constexpr uint32_t OFF_WC = 81920;
constexpr uint32_t OFF_WA = 94720;
constexpr uint32_t OFF_GATE = 145920;
constexpr uint32_t OFF_TT = 146432;
constexpr uint32_t OFF_KVX = 148480;
constexpr uint32_t OFF_CH3 = 163840;
constexpr uint32_t CH_BYTES = 12288, U_BYTES = 4096;
constexpr uint32_t OFF_FT = 225280, OFF_GT = 229376;
constexpr uint32_t OFF_CH0 = 188416;
constexpr uint32_t OFF_KVS = OFF_CH0, KVS_V = 4480, KVS_BYTES = 8576;
constexpr uint32_t OFF_YT = 163840;
constexpr uint32_t OFF_BAR = 231936;
constexpr uint32_t SMEM_BYTES = OFF_BAR + 512;

enum : uint32_t {
  B_EMPTY1 = 0, B_S3 = 3, B_E3 = 4, B_EMPTY2 = 5, B_ATTN = 9, B_P1 = 10,
  B_GATE = 11, B_HA = 12, B_KVD = 13, B_PREP = 14, B_YST = 15,
  B_CVD = 20,
  B_FULL2 = 21, B_U = 29, B_KV = 33, B_HB = 38, B_C34 = 39, B_YRB = 40, B_YFULL = 41, B_EPOCH = 42, B_LAST = 43, B_OSIG = 44,
  B_WOP = 45, B_USIG = 46, B_WST = 47, B_QF = 48, B_ORB = 49, B_YSIG = 50,
  B_F0 = 51, B_FULL1 = 52
};
constexpr uint32_t OFF_EPOCH = OFF_BAR + 8 * 58, OFF_D = OFF_BAR + 8 * 60;
__device__ __forceinline__ uint32_t off_o(int j) { return j < 4 ? OFF_OA + j * O_BYTES : j < 6 ? OFF_CH0 + (j - 4) * O_BYTES : OFF_OA + (j - 6) * O_BYTES; }
__device__ __forceinline__ uint32_t off_w(int j) { return j < 4 ? OFF_WA + j * WO_BYTES : j == 4 ? OFF_KVX : j == 5 ? OFF_WC : OFF_WA + (j - 6) * WO_BYTES; }
__device__ __forceinline__ int step_src(int hg, int j) { return j == 0 ? hg : j <= hg ? j - 1 : j; }
__device__ __forceinline__ bool tail_first(int hg) { return (hg & 3) == 3; }
__device__ __forceinline__ uint32_t off_ch(int c) { return (c < 3 ? OFF_CH0 : OFF_CH3 - 3 * CH_BYTES) + c * CH_BYTES; }

#define U_PITCH 264
__device__ __align__(1024) uint4 g_U[DIM * U_PITCH];
__device__ __align__(128) uint4 g_O[NCTA * 1280];
__device__ uint4 g_WO[64 * 800];
__device__ uint4 g_halo[NCTA * 2 * 7 * 32];
__device__ __align__(128) float g_gate[SEQ];
__device__ unsigned g_cnt[32 * (1 + 2 * 16 + 8 + NCTA)];
constexpr int C_LAUNCH = 0, C_PREP = 32, C_Y = 32 * 17, C_W = 32 * 33, C_O = 32 * 41;

#define TSM(cond, slot) do { } while (0)
#define TSIF(cond, slot) do { if (__LINE__ >= FENCE_LO && __LINE__ < FENCE_HI) sched_fence(); } while (0)
__device__ __forceinline__ void sched_fence() {
  asm volatile("{\n.reg .pred p;\n.reg .u32 c;\nmov.u32 c, %%clock;\nsetp.eq.u32 p, c, 0;\n@p st.shared.u32 [%0], c;\n}"
               ::"r"(1024 + OFF_EPOCH + 4) : "memory");
}
#define TS(slot) TSIF(true, slot)

struct Params {
  const __nv_bfloat16 *q, *k, *v, *shift_k, *ssm_k, *ssm_D, *wqkv, *wo, *gate_w;
  __nv_bfloat16* out;
  uint32_t zero;
};

constexpr int SPIN_LIMIT = 1 << 17;

__device__ __forceinline__ void mbar_init(uint32_t bar, uint32_t count) {
  asm volatile("mbarrier.init.shared::cta.b64 [%0], %1;" ::"r"(bar), "r"(count) : "memory");
}
__device__ __forceinline__ void mbar_expect_tx(uint32_t bar, uint32_t bytes) {
  asm volatile("mbarrier.arrive.expect_tx.shared::cta.b64 _, [%0], %1;" ::"r"(bar), "r"(bytes) : "memory");
}
__device__ __forceinline__ void mbar_arrive(uint32_t bar) {
  asm volatile("mbarrier.arrive.shared::cta.b64 _, [%0];" ::"r"(bar) : "memory");
}
__device__ __forceinline__ void mbar_wait(uint32_t bar, uint32_t parity) {
  uint32_t ok;
  int spins = 0;
  do {
      asm volatile("{\n.reg .pred p;\nmbarrier.try_wait.parity.shared::cta.b64 p, [%1], %2;\nselp.b32 %0, 1, 0, p;\n}"
                   : "=r"(ok) : "r"(bar), "r"(parity) : "memory");
    if (++spins > SPIN_LIMIT) break;
  } while (!ok);
}
__device__ __forceinline__ unsigned flag_read(const unsigned* p) {
  unsigned v;
  asm volatile("ld.relaxed.gpu.global.u32 %0, [%1];" : "=r"(v) : "l"(p) : "memory");
  return v;
}
__device__ __forceinline__ void flag_poll(const unsigned* p, unsigned target) {
  unsigned v;
  int spins = 0;
  do {
    asm volatile("ld.relaxed.gpu.global.u32 %0, [%1];" : "=r"(v) : "l"(p) : "memory");
    if (++spins > SPIN_LIMIT) break;
  } while ((int)(v - target) < 0);
}
__device__ __forceinline__ void flag_wait(const unsigned* p, unsigned target) {
  flag_poll(p, target);
}
__device__ __forceinline__ void flag_signal(unsigned* p, int n, int lane) {
  if (lane == 0) asm volatile("fence.release.gpu;" ::: "memory");
  __syncwarp();
  if (lane < n) asm volatile("red.relaxed.gpu.global.add.u32 [%0], 1;" ::"l"(p + 32 * lane) : "memory");
}
__device__ __forceinline__ void flag_bump(unsigned* p) {
  asm volatile("red.relaxed.gpu.global.add.u32 [%0], 1;" ::"l"(p) : "memory");
}
__device__ __forceinline__ void fence_async_smem() { asm volatile("fence.proxy.async.shared::cta;" ::: "memory"); }
__device__ __forceinline__ void wg_sync(int id) { asm volatile("bar.sync %0, 128;" ::"r"(id) : "memory"); }

__device__ __forceinline__ void tma_2d(uint32_t dst, const CUtensorMap* tm, int c0, int c1, uint32_t bar) {
  asm volatile("cp.async.bulk.tensor.2d.shared::cluster.global.mbarrier::complete_tx::bytes [%0], [%1, {%3, %4}], [%2];"
               ::"r"(dst), "l"(tm), "r"(bar), "r"(c0), "r"(c1) : "memory");
}
__device__ __forceinline__ void tma_3d(uint32_t dst, const CUtensorMap* tm, int c0, int c1, int c2, uint32_t bar) {
  asm volatile("cp.async.bulk.tensor.3d.shared::cluster.global.mbarrier::complete_tx::bytes [%0], [%1, {%3, %4, %5}], [%2];"
               ::"r"(dst), "l"(tm), "r"(bar), "r"(c0), "r"(c1), "r"(c2) : "memory");
}
__device__ __forceinline__ void bulk_load(uint32_t dst, const void* src, uint32_t bytes, uint32_t bar) {
  asm volatile("cp.async.bulk.shared::cluster.global.mbarrier::complete_tx::bytes [%0], [%1], %2, [%3];"
               ::"r"(dst), "l"(src), "r"(bytes), "r"(bar) : "memory");
}
__device__ __forceinline__ void bulk_store(void* dst, uint32_t src, uint32_t bytes) {
  asm volatile("cp.async.bulk.global.shared::cta.bulk_group [%0], [%1], %2;" ::"l"(dst), "r"(src), "r"(bytes) : "memory");
}
__device__ __forceinline__ void bulk_wait_read() {
  asm volatile("cp.async.bulk.commit_group;\ncp.async.bulk.wait_group.read 0;" ::: "memory");
}

__device__ __forceinline__ void publish(void* dst, uint32_t src, uint32_t bytes, uint32_t bar) {
  bulk_store(dst, src, bytes);
  bulk_wait_read();
  bulk_load(src, dst, bytes, bar);
}

__device__ __forceinline__ void wg_fence() { asm volatile("wgmma.fence.sync.aligned;" ::: "memory"); }
__device__ __forceinline__ void wg_commit() { asm volatile("wgmma.commit_group.sync.aligned;" ::: "memory"); }
template <int N> __device__ __forceinline__ void wg_wait() { asm volatile("wgmma.wait_group.sync.aligned %0;" ::"n"(N) : "memory"); }
__device__ __forceinline__ uint32_t desc_lo(uint32_t addr, uint32_t lbo) { return ((addr & 0x3FFFF) >> 4) | ((lbo >> 4) << 16); }
constexpr uint32_t desc_hi(uint32_t sbo, uint32_t swz) { return (sbo >> 4) | (swz << 30); }
constexpr uint32_t HI_SW128 = desc_hi(1024, 1), HI_SW64 = desc_hi(512, 2), HI_SW32 = desc_hi(256, 3), HI_NONE = desc_hi(128, 0);
template <int N> __device__ __forceinline__ void pin(float* d) {
#pragma unroll
  for (int i = 0; i < N; i++) asm volatile("" : "+f"(d[i])::"memory");
}

__device__ __forceinline__ uint32_t lds32(uint32_t a) {
  uint32_t v;
  asm volatile("ld.volatile.shared.u32 %0, [%1];" : "=r"(v) : "r"(a) : "memory");
  return v;
}
__device__ __forceinline__ uint2 ldg64(const void* a) {
  uint2 v;
  asm volatile("ld.global.nc.v2.u32 {%0, %1}, [%2];" : "=r"(v.x), "=r"(v.y) : "l"(a) : "memory");
  return v;
}
__device__ __forceinline__ void ldsm4(uint32_t* r, uint32_t a) {
  asm volatile("ldmatrix.sync.aligned.m8n8.x4.shared.b16 {%0, %1, %2, %3}, [%4];"
               : "=r"(r[0]), "=r"(r[1]), "=r"(r[2]), "=r"(r[3]) : "r"(a) : "memory");
}
__device__ __forceinline__ void ldsm4t(uint32_t* r, uint32_t a) {
  asm volatile("ldmatrix.sync.aligned.m8n8.x4.trans.shared.b16 {%0, %1, %2, %3}, [%4];"
               : "=r"(r[0]), "=r"(r[1]), "=r"(r[2]), "=r"(r[3]) : "r"(a) : "memory");
}
__device__ __forceinline__ uint2 lds64(uint32_t a) {
  uint2 v;
  asm volatile("ld.shared.v2.u32 {%0, %1}, [%2];" : "=r"(v.x), "=r"(v.y) : "r"(a) : "memory");
  return v;
}
__device__ __forceinline__ uint4 lds128(uint32_t a) {
  uint4 v;
  asm volatile("ld.shared.v4.u32 {%0, %1, %2, %3}, [%4];" : "=r"(v.x), "=r"(v.y), "=r"(v.z), "=r"(v.w) : "r"(a) : "memory");
  return v;
}
__device__ __forceinline__ void sts128(uint32_t a, uint32_t x, uint32_t y, uint32_t z, uint32_t w) {
  asm volatile("st.shared.v4.u32 [%0], {%1, %2, %3, %4};" ::"r"(a), "r"(x), "r"(y), "r"(z), "r"(w) : "memory");
}
__device__ __forceinline__ void stsm4(uint32_t a, const uint32_t* r) {
  asm volatile("stmatrix.sync.aligned.m8n8.x4.shared.b16 [%0], {%1, %2, %3, %4};" ::"r"(a), "r"(r[0]), "r"(r[1]), "r"(r[2]), "r"(r[3]) : "memory");
}
__device__ __forceinline__ uint32_t pack2(float lo, float hi) {
  uint32_t r;
  asm("cvt.rn.bf16x2.f32 %0, %1, %2;" : "=r"(r) : "f"(hi), "f"(lo));
  return r;
}
__device__ __forceinline__ uint32_t movm(uint32_t a) {
  uint32_t d;
  asm volatile("movmatrix.sync.aligned.m8n8.trans.b16 %0, %1;" : "=r"(d) : "r"(a));
  return d;
}
__device__ __forceinline__ uint32_t bmul(uint32_t a, uint32_t b) {
  uint32_t d;
  asm("mul.rn.bf16x2 %0, %1, %2;" : "=r"(d) : "r"(a), "r"(b));
  return d;
}
__device__ __forceinline__ uint32_t badd(uint32_t a, uint32_t b) {
  uint32_t d;
  asm("add.rn.bf16x2 %0, %1, %2;" : "=r"(d) : "r"(a), "r"(b));
  return d;
}
__device__ __forceinline__ uint32_t bfma(uint32_t a, uint32_t b, uint32_t c) {
  uint32_t d;
  asm("fma.rn.bf16x2 %0, %1, %2, %3;" : "=r"(d) : "r"(a), "r"(b), "r"(c));
  return d;
}
__device__ __forceinline__ float bf_lo(uint32_t x) { return __uint_as_float(x << 16); }
__device__ __forceinline__ float bf_hi(uint32_t x) { return __uint_as_float(x & 0xFFFF0000u); }
__device__ __forceinline__ float ex2(float x) {
  float y;
  asm("ex2.approx.ftz.f32 %0, %1;" : "=f"(y) : "f"(x));
  return y;
}
__device__ __forceinline__ float rcp(float x) {
  float y;
  asm("rcp.approx.ftz.f32 %0, %1;" : "=f"(y) : "f"(x));
  return y;
}
__device__ __forceinline__ void mma16816(float* d, uint32_t a0, uint32_t a1, uint32_t a2, uint32_t a3, uint32_t b0, uint32_t b1) {
  asm volatile("mma.sync.aligned.m16n8k16.row.col.f32.bf16.bf16.f32 {%0, %1, %2, %3}, {%4, %5, %6, %7}, {%8, %9}, {%0, %1, %2, %3};"
               : "+f"(d[0]), "+f"(d[1]), "+f"(d[2]), "+f"(d[3])
               : "r"(a0), "r"(a1), "r"(a2), "r"(a3), "r"(b0), "r"(b1));
}
__device__ __forceinline__ void mma1688(float* d, uint32_t a0, uint32_t a1, uint32_t b0) {
  asm volatile("mma.sync.aligned.m16n8k8.row.col.f32.bf16.bf16.f32 {%0, %1, %2, %3}, {%4, %5}, {%6}, {%0, %1, %2, %3};"
               : "+f"(d[0]), "+f"(d[1]), "+f"(d[2]), "+f"(d[3])
               : "r"(a0), "r"(a1), "r"(b0));
}

template <int N> struct WgRS;
template <int N> struct WgSST;
template <> struct WgRS<32> {
  template <uint32_t HB>
  static __device__ __forceinline__ void mma(float* d, const uint32_t* a, uint32_t db) {
    asm volatile("{\n.reg .pred p;\n.reg .b64 db;\nsetp.ne.b32 p, %22, 0;\n"
      "mov.b64 db, {%20, %21};\n"
      "wgmma.mma_async.sync.aligned.m64n32k16.f32.bf16.bf16 {"
      "%0, %1, %2, %3, %4, %5, %6, %7, %8, %9, %10, %11, %12, %13, %14, %15"
      "}, {%16, %17, %18, %19}, db, p, 1, 1, 1;\n}\n"
      : "+f"(d[0]), "+f"(d[1]), "+f"(d[2]), "+f"(d[3]), "+f"(d[4]), "+f"(d[5]), "+f"(d[6]), "+f"(d[7]),
        "+f"(d[8]), "+f"(d[9]), "+f"(d[10]), "+f"(d[11]), "+f"(d[12]), "+f"(d[13]), "+f"(d[14]), "+f"(d[15])
      : "r"(a[0]), "r"(a[1]), "r"(a[2]), "r"(a[3]), "r"(db), "n"(HB), "n"(1));
  }
  template <uint32_t HB>
  static __device__ __forceinline__ void set(float* d, const uint32_t* a, uint32_t db) {
    asm volatile("{\n.reg .pred p;\n.reg .b64 db;\nsetp.ne.b32 p, %22, 0;\n"
      "mov.b64 db, {%20, %21};\n"
      "wgmma.mma_async.sync.aligned.m64n32k16.f32.bf16.bf16 {"
      "%0, %1, %2, %3, %4, %5, %6, %7, %8, %9, %10, %11, %12, %13, %14, %15"
      "}, {%16, %17, %18, %19}, db, p, 1, 1, 1;\n}\n"
      : "=f"(d[0]), "=f"(d[1]), "=f"(d[2]), "=f"(d[3]), "=f"(d[4]), "=f"(d[5]), "=f"(d[6]), "=f"(d[7]),
        "=f"(d[8]), "=f"(d[9]), "=f"(d[10]), "=f"(d[11]), "=f"(d[12]), "=f"(d[13]), "=f"(d[14]), "=f"(d[15])
      : "r"(a[0]), "r"(a[1]), "r"(a[2]), "r"(a[3]), "r"(db), "n"(HB), "n"(0));
  }
};
template <> struct WgRS<64> {
  template <uint32_t HB>
  static __device__ __forceinline__ void mma(float* d, const uint32_t* a, uint32_t db) {
    asm volatile("{\n.reg .pred p;\n.reg .b64 db;\nsetp.ne.b32 p, %38, 0;\n"
      "mov.b64 db, {%36, %37};\n"
      "wgmma.mma_async.sync.aligned.m64n64k16.f32.bf16.bf16 {"
      "%0, %1, %2, %3, %4, %5, %6, %7, %8, %9, %10, %11, %12, %13, %14, %15, "
      "%16, %17, %18, %19, %20, %21, %22, %23, %24, %25, %26, %27, %28, %29, %30, %31"
      "}, {%32, %33, %34, %35}, db, p, 1, 1, 1;\n}\n"
      : "+f"(d[0]), "+f"(d[1]), "+f"(d[2]), "+f"(d[3]), "+f"(d[4]), "+f"(d[5]), "+f"(d[6]), "+f"(d[7]),
        "+f"(d[8]), "+f"(d[9]), "+f"(d[10]), "+f"(d[11]), "+f"(d[12]), "+f"(d[13]), "+f"(d[14]), "+f"(d[15]),
        "+f"(d[16]), "+f"(d[17]), "+f"(d[18]), "+f"(d[19]), "+f"(d[20]), "+f"(d[21]), "+f"(d[22]), "+f"(d[23]),
        "+f"(d[24]), "+f"(d[25]), "+f"(d[26]), "+f"(d[27]), "+f"(d[28]), "+f"(d[29]), "+f"(d[30]), "+f"(d[31])
      : "r"(a[0]), "r"(a[1]), "r"(a[2]), "r"(a[3]), "r"(db), "n"(HB), "n"(1));
  }
  template <uint32_t HB>
  static __device__ __forceinline__ void set(float* d, const uint32_t* a, uint32_t db) {
    asm volatile("{\n.reg .pred p;\n.reg .b64 db;\nsetp.ne.b32 p, %38, 0;\n"
      "mov.b64 db, {%36, %37};\n"
      "wgmma.mma_async.sync.aligned.m64n64k16.f32.bf16.bf16 {"
      "%0, %1, %2, %3, %4, %5, %6, %7, %8, %9, %10, %11, %12, %13, %14, %15, "
      "%16, %17, %18, %19, %20, %21, %22, %23, %24, %25, %26, %27, %28, %29, %30, %31"
      "}, {%32, %33, %34, %35}, db, p, 1, 1, 1;\n}\n"
      : "=f"(d[0]), "=f"(d[1]), "=f"(d[2]), "=f"(d[3]), "=f"(d[4]), "=f"(d[5]), "=f"(d[6]), "=f"(d[7]),
        "=f"(d[8]), "=f"(d[9]), "=f"(d[10]), "=f"(d[11]), "=f"(d[12]), "=f"(d[13]), "=f"(d[14]), "=f"(d[15]),
        "=f"(d[16]), "=f"(d[17]), "=f"(d[18]), "=f"(d[19]), "=f"(d[20]), "=f"(d[21]), "=f"(d[22]), "=f"(d[23]),
        "=f"(d[24]), "=f"(d[25]), "=f"(d[26]), "=f"(d[27]), "=f"(d[28]), "=f"(d[29]), "=f"(d[30]), "=f"(d[31])
      : "r"(a[0]), "r"(a[1]), "r"(a[2]), "r"(a[3]), "r"(db), "n"(HB), "n"(0));
  }
};
template <> struct WgSST<48> {
  template <uint32_t HA, uint32_t HB>
  static __device__ __forceinline__ void mma(float* d, uint32_t da, uint32_t db, int sc) {
    asm volatile("{\n.reg .pred p;\n.reg .b64 da, db;\nsetp.ne.b32 p, %28, 0;\n"
      "mov.b64 da, {%24, %25};\nmov.b64 db, {%26, %27};\n"
      "wgmma.mma_async.sync.aligned.m64n48k16.f32.bf16.bf16 {"
      "%0, %1, %2, %3, %4, %5, %6, %7, %8, %9, %10, %11, %12, %13, %14, %15, "
      "%16, %17, %18, %19, %20, %21, %22, %23"
      "}, da, db, p, 1, 1, 0, 1;\n}\n"
      : "+f"(d[0]), "+f"(d[1]), "+f"(d[2]), "+f"(d[3]), "+f"(d[4]), "+f"(d[5]), "+f"(d[6]), "+f"(d[7]),
        "+f"(d[8]), "+f"(d[9]), "+f"(d[10]), "+f"(d[11]), "+f"(d[12]), "+f"(d[13]), "+f"(d[14]), "+f"(d[15]),
        "+f"(d[16]), "+f"(d[17]), "+f"(d[18]), "+f"(d[19]), "+f"(d[20]), "+f"(d[21]), "+f"(d[22]), "+f"(d[23])
      : "r"(da), "n"(HA), "r"(db), "n"(HB), "r"(sc));
  }
};
template <> struct WgSST<80> {
  template <uint32_t HA, uint32_t HB>
  static __device__ __forceinline__ void mma(float* d, uint32_t da, uint32_t db, int sc) {
    asm volatile("{\n.reg .pred p;\n.reg .b64 da, db;\nsetp.ne.b32 p, %44, 0;\n"
      "mov.b64 da, {%40, %41};\nmov.b64 db, {%42, %43};\n"
      "wgmma.mma_async.sync.aligned.m64n80k16.f32.bf16.bf16 {"
      "%0, %1, %2, %3, %4, %5, %6, %7, %8, %9, %10, %11, %12, %13, %14, %15, "
      "%16, %17, %18, %19, %20, %21, %22, %23, %24, %25, %26, %27, %28, %29, %30, %31, "
      "%32, %33, %34, %35, %36, %37, %38, %39"
      "}, da, db, p, 1, 1, 0, 1;\n}\n"
      : "+f"(d[0]), "+f"(d[1]), "+f"(d[2]), "+f"(d[3]), "+f"(d[4]), "+f"(d[5]), "+f"(d[6]), "+f"(d[7]),
        "+f"(d[8]), "+f"(d[9]), "+f"(d[10]), "+f"(d[11]), "+f"(d[12]), "+f"(d[13]), "+f"(d[14]), "+f"(d[15]),
        "+f"(d[16]), "+f"(d[17]), "+f"(d[18]), "+f"(d[19]), "+f"(d[20]), "+f"(d[21]), "+f"(d[22]), "+f"(d[23]),
        "+f"(d[24]), "+f"(d[25]), "+f"(d[26]), "+f"(d[27]), "+f"(d[28]), "+f"(d[29]), "+f"(d[30]), "+f"(d[31]),
        "+f"(d[32]), "+f"(d[33]), "+f"(d[34]), "+f"(d[35]), "+f"(d[36]), "+f"(d[37]), "+f"(d[38]), "+f"(d[39])
      : "r"(da), "n"(HA), "r"(db), "n"(HB), "r"(sc));
  }
};
template <> struct WgSST<192> {
  template <uint32_t HA, uint32_t HB>
  static __device__ __forceinline__ void mma(float* d, uint32_t da, uint32_t db, int sc) {
    asm volatile("{\n.reg .pred p;\n.reg .b64 da, db;\nsetp.ne.b32 p, %100, 0;\n"
      "mov.b64 da, {%96, %97};\nmov.b64 db, {%98, %99};\n"
      "wgmma.mma_async.sync.aligned.m64n192k16.f32.bf16.bf16 {"
      "%0, %1, %2, %3, %4, %5, %6, %7, %8, %9, %10, %11, %12, %13, %14, %15, "
      "%16, %17, %18, %19, %20, %21, %22, %23, %24, %25, %26, %27, %28, %29, %30, %31, "
      "%32, %33, %34, %35, %36, %37, %38, %39, %40, %41, %42, %43, %44, %45, %46, %47, "
      "%48, %49, %50, %51, %52, %53, %54, %55, %56, %57, %58, %59, %60, %61, %62, %63, "
      "%64, %65, %66, %67, %68, %69, %70, %71, %72, %73, %74, %75, %76, %77, %78, %79, "
      "%80, %81, %82, %83, %84, %85, %86, %87, %88, %89, %90, %91, %92, %93, %94, %95"
      "}, da, db, p, 1, 1, 0, 1;\n}\n"
      : "+f"(d[0]), "+f"(d[1]), "+f"(d[2]), "+f"(d[3]), "+f"(d[4]), "+f"(d[5]), "+f"(d[6]), "+f"(d[7]),
        "+f"(d[8]), "+f"(d[9]), "+f"(d[10]), "+f"(d[11]), "+f"(d[12]), "+f"(d[13]), "+f"(d[14]), "+f"(d[15]),
        "+f"(d[16]), "+f"(d[17]), "+f"(d[18]), "+f"(d[19]), "+f"(d[20]), "+f"(d[21]), "+f"(d[22]), "+f"(d[23]),
        "+f"(d[24]), "+f"(d[25]), "+f"(d[26]), "+f"(d[27]), "+f"(d[28]), "+f"(d[29]), "+f"(d[30]), "+f"(d[31]),
        "+f"(d[32]), "+f"(d[33]), "+f"(d[34]), "+f"(d[35]), "+f"(d[36]), "+f"(d[37]), "+f"(d[38]), "+f"(d[39]),
        "+f"(d[40]), "+f"(d[41]), "+f"(d[42]), "+f"(d[43]), "+f"(d[44]), "+f"(d[45]), "+f"(d[46]), "+f"(d[47]),
        "+f"(d[48]), "+f"(d[49]), "+f"(d[50]), "+f"(d[51]), "+f"(d[52]), "+f"(d[53]), "+f"(d[54]), "+f"(d[55]),
        "+f"(d[56]), "+f"(d[57]), "+f"(d[58]), "+f"(d[59]), "+f"(d[60]), "+f"(d[61]), "+f"(d[62]), "+f"(d[63]),
        "+f"(d[64]), "+f"(d[65]), "+f"(d[66]), "+f"(d[67]), "+f"(d[68]), "+f"(d[69]), "+f"(d[70]), "+f"(d[71]),
        "+f"(d[72]), "+f"(d[73]), "+f"(d[74]), "+f"(d[75]), "+f"(d[76]), "+f"(d[77]), "+f"(d[78]), "+f"(d[79]),
        "+f"(d[80]), "+f"(d[81]), "+f"(d[82]), "+f"(d[83]), "+f"(d[84]), "+f"(d[85]), "+f"(d[86]), "+f"(d[87]),
        "+f"(d[88]), "+f"(d[89]), "+f"(d[90]), "+f"(d[91]), "+f"(d[92]), "+f"(d[93]), "+f"(d[94]), "+f"(d[95])
      : "r"(da), "n"(HA), "r"(db), "n"(HB), "r"(sc));
  }
};

struct FftConst {
  uint32_t f[2][4], fi[4][4];
  uint32_t ta[2][2], tb[2][2];
};
__device__ __forceinline__ void cis(int m, float scale, float& c, float& s) {
  const float a = (float)m * (-6.283185307179586f * scale);
  c = __cosf(a);
  s = __sinf(a);
}
__device__ __forceinline__ void fft_tables(uint32_t (&v)[12], int tw) {
  const int row = tw >> 2, ch = tw & 3;
#pragma unroll
  for (int i = 0; i < 4; i++) {
    float c[2], s[2], x[2];
#pragma unroll
    for (int e = 0; e < 2; e++) {
      cis((((32 * (8 * ch + 2 * i + e) + 15) * (4 * row - 63) + 2048) & 4095) - 2048, 1.f / 4096, c[e], s[e]);
      float gc, gs;
      cis((((row & 15) * (8 * (ch & 1) + 2 * i + e) + 8) & 15) - 8, 1.f / 16, gc, gs);
      x[e] = (row >> 4) == (ch >> 1) ? gc : (ch >> 1) ? gs : -gs;
    }
    v[i] = pack2(c[0] * 0.125f, c[1] * 0.125f);
    v[4 + i] = pack2(s[0] * 0.125f, s[1] * 0.125f);
    v[8 + i] = pack2(x[0], x[1]);
  }
#pragma unroll
  for (int i = 0; i < 12; i++) asm volatile("" : "+r"(v[i]));
}
__device__ __forceinline__ void fft_tables_store(const uint32_t (&v)[12], uint32_t sb, int tw) {
  const int row = tw >> 2;
  const uint32_t x = ((tw ^ (row >> 1)) & 3) << 4, a = sb + OFF_FT + (16 * (row >> 3) + (row & 7)) * 64 + x;
  sts128(a, v[0], v[1], v[2], v[3]);
  sts128(a + 512, v[4], v[5], v[6], v[7]);
  sts128(sb + OFF_GT + row * 64 + x, v[8], v[9], v[10], v[11]);
}
__device__ __forceinline__ void fft_twiddles(uint32_t (&v)[2], int tw) {
  float a[2], s[2];
#pragma unroll
  for (int i = 0; i < 2; i++) {
    float c;
    cis((2 * (2 * (tw & 3) + i) - 15) * (4 * (tw >> 2) - 63), 1.f / 4096, c, s[i]);
    a[i] = __fdividef(-s[i], 1.f + c);
  }
  v[0] = pack2(a[0], a[1]);
  v[1] = pack2(s[0], s[1]);
  asm volatile("" : "+r"(v[0]), "+r"(v[1]));
}
__device__ __forceinline__ void fft_matrices(FftConst& k, uint32_t sb, int w, int lane) {
  const uint32_t x = (lane >> 1) & 3;
  const uint2 t0 = lds64(sb + OFF_TT + 256 * w + 8 * lane), t1 = lds64(sb + OFF_TT + 256 * w + 8 * (lane ^ 3));
  k.ta[0][0] = t0.x;
  k.tb[0][0] = t0.y;
  k.ta[1][1] = __byte_perm(t1.x, 0, 0x1032);
  k.tb[1][1] = __byte_perm(t1.y, 0, 0x1032);
#pragma unroll
  for (int j = 0; j < 2; j++) {
    k.ta[1 - j][j] = k.ta[j][j] ^ 0x80008000u;
    k.tb[1 - j][j] = k.tb[j][j] ^ 0x80008000u;
    asm volatile("" : "+r"(k.ta[0][j]), "+r"(k.tb[0][j]), "+r"(k.ta[1][j]), "+r"(k.tb[1][j]));
  }
#pragma unroll
  for (int i = 0; i < 2; i++) {
    ldsm4(k.f[i], sb + OFF_FT + (16 * w + (lane & 15)) * 64 + (((2 * i + (lane >> 4)) ^ x) << 4));
    ldsm4t(k.fi[i], sb + OFF_FT + (32 * i + lane) * 64 + ((w ^ x) << 4));
#pragma unroll
    for (int j = 0; j < 4; j++) {
      k.fi[2 + i][j] = (j & 1) ? k.fi[i][j - 1] ^ 0x80008000u : k.fi[i][j + 1];
      asm volatile("" : "+r"(k.fi[2 + i][j]));
    }
  }
}
__device__ __forceinline__ void rot(uint32_t& x, uint32_t& y, uint32_t a, uint32_t b) {
  x = bfma(a, y, x);
  y = bfma(b, x, y);
  x = bfma(a, y, x);
}
__device__ __forceinline__ void twiddle_fwd(uint32_t (&a)[4][4], float* d, const FftConst& k) {
#pragma unroll
  for (int q = 0; q < 4; q++)
#pragma unroll
    for (int j = 0; j < 2; j++) {
      const float* x = d + 8 * q + 4 * j;
      uint32_t re = pack2(x[0], x[1]), im = pack2(x[2], x[3]);
      rot(re, im, k.ta[0][j], k.tb[0][j]);
      a[q & 2][2 * j + (q & 1)] = re;
      a[(q & 2) + 1][2 * j + (q & 1)] = im;
    }
}
__device__ __forceinline__ void g_step(float* d, const uint32_t (&a)[4][4], uint32_t dre, uint32_t dim) {
  WgRS<32>::set<HI_SW64>(d, a[0], dre);
  WgRS<32>::set<HI_SW64>(d + 16, a[2], dre);
  WgRS<32>::mma<HI_SW64>(d, a[1], dim);
  WgRS<32>::mma<HI_SW64>(d + 16, a[3], dim);
  wg_commit();
}

__device__ __forceinline__ void products(uint32_t (&a)[4][4], const float* H, const float* U, int p) {
#pragma unroll
  for (int j = 0; j < 2; j++)
#pragma unroll
    for (int m = 2 * p; m < 2 * p + 2; m++) {
      float pr[2], pi[2];
#pragma unroll
      for (int x = 0; x < 2; x++)
#pragma unroll
        for (int q = 0; q <= m; q++) {
          const int ih = 16 * (q >> 1) + 2 * (q & 1) + 4 * j + x, iu = 16 * ((m - q) >> 1) + 2 * ((m - q) & 1) + 4 * j + x;
          pr[x] = q ? fmaf(H[ih], U[iu], pr[x]) : H[ih] * U[iu];
          pi[x] = q ? fmaf(H[ih], U[iu + 8], pi[x]) : H[ih] * U[iu + 8];
          pr[x] = fmaf(-H[ih + 8], U[iu + 8], pr[x]);
          pi[x] = fmaf(H[ih + 8], U[iu], pi[x]);
        }
      a[m & 2][2 * j + (m & 1)] = pack2(pr[0], pr[1]);
      a[(m & 2) + 1][2 * j + (m & 1)] = pack2(pi[0], pi[1]);
    }
}

__device__ __forceinline__ void conv_channel(const FftConst& k, uint32_t sb, int c, int wg, int w, int lane) {
  const uint32_t cb = sb + off_ch(c), bars = sb + OFF_BAR;
  const uint32_t du = desc_lo(cb, 1024), dg = desc_lo(sb + OFF_GT, 16), dz = desc_lo(cb + U_BYTES, 16);
  float U[32], H[32];
  uint32_t a[4][4], e[4][4];
  const float dv = __uint_as_float(lds32(sb + OFF_D + 4 * c));
  wg_fence();
  WgRS<64>::set<HI_SW32>(H, k.f[0], du + 256);
  WgRS<64>::mma<HI_SW32>(H, k.f[1], du + 256 + 32);
  wg_commit();
  wg_wait<0>();
  pin<32>(H);
  twiddle_fwd(a, H, k);
  mbar_wait(bars + 8 * (B_U + (c < 3 ? c : 3)), 0);
  TSM(w == 0 && c < 3, 7 + wg);
  wg_fence();
  WgRS<64>::set<HI_SW32>(U, k.f[0], du);
  WgRS<64>::mma<HI_SW32>(U, k.f[1], du + 32);
  wg_commit();
  g_step(H, a, dg, dg + 64);
  wg_wait<1>();
  pin<32>(U);
  twiddle_fwd(e, U, k);
  wg_fence();
  g_step(U, e, dg, dg + 64);
  wg_wait<0>();
  pin<32>(U);
  pin<32>(H);
#pragma unroll
  for (int j = 0; j < 4; j++) H[4 * (j >> 1) + (j & 1)] += dv;
  float V[32];
#pragma unroll
  for (int p = 0; p < 2; p++) {
    products(a, H, U, p);
    wg_fence();
    WgRS<32>::set<HI_SW64>(V + 16 * p, a[2 * p], dg + 64);
    WgRS<32>::mma<HI_SW64>(V + 16 * p, a[2 * p + 1], dg);
    wg_commit();
  }
  const uint32_t za = cb + U_BYTES + (8 * w + (lane & 7)) * 128 + (((lane >> 3) ^ (lane & 7)) << 4);
  const uint32_t ya = cb + (lane >> 4) * 1024 + (8 * w + (lane & 7)) * 32 + ((((lane >> 3) ^ (lane >> 2)) & 1) << 4);
  wg_sync(1 + wg);
#pragma unroll
  for (int p = 0; p < 2; p++) {
    if (p == 0) wg_wait<1>();
    else wg_wait<0>();
    pin<16>(V + 16 * p);
#pragma unroll
    for (int i = 0; i < 4; i++) {
      const int j = i & 1;
      const float* x = V + 16 * p + 4 * j + (i & 2);
      e[p][i] = pack2(x[8], x[9]);
      e[2 + p][i] = pack2(x[0], x[1]);
      rot(e[p][i], e[2 + p][i], k.ta[1][j], k.tb[1][j]);
    }
    stsm4(za ^ (64 * p), e[p]);
    stsm4((za ^ (64 * p)) + 4096, e[2 + p]);
  }
  fence_async_smem();
  wg_sync(1 + wg);
  wg_fence();
  WgRS<64>::set<HI_SW128>(H, k.fi[0], dz);
#pragma unroll
  for (int ks = 1; ks < 4; ks++) WgRS<64>::mma<HI_SW128>(H, k.fi[ks], dz + 128 * ks);
  wg_commit();
  wg_wait<0>();
  pin<32>(H);
  if (lane == 0) mbar_arrive(bars + 8 * B_CVD);
  TSIF(w == 0, 88 + c);
#pragma unroll
  for (int j = 0; j < 8; j++)
    a[j >> 2][j & 3] = j < 2 ? pack2(H[4 * j], H[4 * j + 1]) : pack2(H[4 * j] + H[4 * j - 6], H[4 * j + 1] + H[4 * j - 5]);
  stsm4(ya, a[0]);
  stsm4(ya + 2048, a[1]);
  fence_async_smem();
  __syncwarp();
}

__device__ __forceinline__ void prep_slab(uint4* res, const uint2* sw, uint32_t sb, int slab, int w, int lane) {
  const int t = lane & 3, tp = (lane & 7) >> 1, pos = 8 * tp + 2 * (((lane >> 3) + tp) & 3) + (lane & 1);
  const uint32_t base = sb + OFF_KVS + slab * KVS_BYTES + pos * 128;
  uint32_t kk[2][4][4], vv[2][4];
  mbar_wait(sb + OFF_BAR + 8 * (B_KV + slab), 0);
#pragma unroll
  for (int h = 0; h < 2; h++) {
#pragma unroll
    for (int j = 0; j < 4; j++) {
      const uint32_t a = base + 128 * j;
      ldsm4t(kk[h][j], a + (((w + 4 * h) ^ ((a >> 7) & 7)) << 4));
    }
    const uint32_t a = base + KVS_V;
    ldsm4t(vv[h], a + (((w + 4 * h) ^ ((a >> 7) & 7)) << 4));
  }
#pragma unroll
  for (int h = 0; h < 2; h++) {
    uint32_t (&k)[4][4] = kk[h];
    uint32_t (&v)[4] = vv[h];
    const uint32_t w0 = __byte_perm(sw[h].x, 0, 0x1010), w1 = __byte_perm(sw[h].x, 0, 0x3232);
    const uint32_t w2 = __byte_perm(sw[h].y, 0, 0x1010), w3 = __byte_perm(sw[h].y, 0, 0x3232);
#pragma unroll
    for (int m = 0; m < 4; m++)
      v[m] = bmul(badd(badd(badd(bmul(k[0][m], w3), bmul(k[1][m], w2)), bmul(k[2][m], w1)), bmul(k[3][m], w0)), v[m]);
    uint32_t a[4];
#pragma unroll
    for (int m = 0; m < 4; m++) a[m] = (t & 1) ? v[(m + 3) & 3] : v[m];
    res[h] = (t & 2) ? make_uint4(a[2], a[3], a[0], a[1]) : make_uint4(a[0], a[1], a[2], a[3]);
  }
}

__device__ __forceinline__ void prep_gate(const Params& p, uint32_t sb, int b, int w, int lane) {
  uint2 gw[5], x[4][5];
#pragma unroll
  for (int j = 0; j < 5; j++) gw[j] = ldg64(reinterpret_cast<const uint2*>(p.gate_w) + lane + 32 * j);
#pragma unroll
  for (int i = 0; i < 4; i++)
#pragma unroll
    for (int j = 0; j < 5; j++)
      x[i][j] = ldg64(reinterpret_cast<const uint2*>(p.q) + (16 * b + 4 * w + i) * (DIM / 4) + lane + 32 * j);
  float s[4];
#pragma unroll
  for (int i = 0; i < 4; i++) {
    s[i] = 0.f;
#pragma unroll
    for (int j = 0; j < 5; j++) {
      const uint32_t m0 = bmul(x[i][j].x, gw[j].x), m1 = bmul(x[i][j].y, gw[j].y);
      s[i] += (bf_lo(m0) + bf_hi(m0)) + (bf_lo(m1) + bf_hi(m1));
    }
  }
  const bool h = lane & 16, q = lane & 8;
  const float a = (h ? s[2] : s[0]) + __shfl_xor_sync(0xffffffffu, h ? s[0] : s[2], 16);
  const float c = (h ? s[3] : s[1]) + __shfl_xor_sync(0xffffffffu, h ? s[1] : s[3], 16);
  float z = (q ? c : a) + __shfl_xor_sync(0xffffffffu, q ? a : c, 8);
#pragma unroll
  for (int o = 4; o > 0; o >>= 1) z += __shfl_xor_sync(0xffffffffu, z, o);
  z = bf_lo(pack2(z, 0.f));
  z = bf_lo(pack2(__fdividef(1.f, 1.f + __expf(-z)), 0.f));
  mbar_wait(sb + OFF_BAR + 8 * B_S3, 0);
  if ((lane & 7) == 0) asm volatile("st.shared.f32 [%0], %1;" ::"r"(sb + OFF_GATE + 64 * (b & 7) + 16 * w + (lane >> 1)), "f"(z) : "memory");
  fence_async_smem();
}

__device__ __forceinline__ uint32_t bmax(uint32_t a, uint32_t b) {
  uint32_t d;
  asm("max.bf16x2 %0, %1, %2;" : "=r"(d) : "r"(a), "r"(b));
  return d;
}
__device__ __forceinline__ void softmax_two(const float (&l)[2][2], uint32_t& p0, uint32_t& p1) {
  constexpr float kScale = 0.22360679774997896f, kLog2e = 1.4426950408889634f;
  const uint32_t r0 = pack2(l[0][0], l[1][0]), r1 = pack2(l[0][1], l[1][1]);
  const uint32_t x0 = pack2(bf_lo(r0) * kScale, bf_hi(r0) * kScale), x1 = pack2(bf_lo(r1) * kScale, bf_hi(r1) * kScale);
  uint32_t m = bmax(x0, x1);
  m = bmax(m, __shfl_xor_sync(0xffffffffu, m, 1));
  m = bmax(m, __shfl_xor_sync(0xffffffffu, m, 2));
  const float m0 = bf_lo(m) * kLog2e, m1 = bf_hi(m) * kLog2e;
  p0 = pack2(ex2(bf_lo(x0) * kLog2e - m0), ex2(bf_lo(x1) * kLog2e - m0));
  p1 = pack2(ex2(bf_hi(x0) * kLog2e - m1), ex2(bf_hi(x1) * kLog2e - m1));
}

__device__ __forceinline__ void halo_read(uint32_t (&kpv)[10], uint32_t (&vpv)[10], uint32_t (&tg)[7], const uint4* hp) {
#pragma unroll
  for (int j = 0; j < 7; j++) {
    uint32_t x0, x1, x2;
    asm volatile("ld.relaxed.gpu.global.v4.u32 {%0, %1, %2, %3}, [%4];"
                 : "=r"(x0), "=r"(x1), "=r"(x2), "=r"(tg[j]) : "l"(hp + 32 * j) : "memory");
    if (j < 4) kpv[3 * j] = x0; else vpv[3 * j - 10] = x0;
    if (j < 3) kpv[3 * j + 1] = x1; else vpv[3 * j - 9] = x1;
    if (j < 3) kpv[3 * j + 2] = x2; else if (j < 6) vpv[3 * j - 8] = x2;
  }
}

template <int ROT>
__device__ __forceinline__ void pack_qkv(const float* acc, uint32_t (&qlo)[10], uint32_t (&qhi)[10], uint32_t (&klo)[10],
                                         uint32_t (&khi)[10], uint32_t (&vlo)[10], uint32_t (&vhi)[10]) {
#pragma unroll
  for (int j = 0; j < 10; j++) {
    const int x = (j + ROT) % 10, tq = x < 8 ? x : 16 + x, tk = x < 8 ? 8 + x : 18 + x, tv = x < 8 ? 16 + x : 20 + x;
    khi[j] = pack2(acc[4 * tk + 2], acc[4 * tk + 3]);
    vhi[j] = movm(pack2(acc[4 * tv + 2], acc[4 * tv + 3]));
    qlo[j] = pack2(acc[4 * tq], acc[4 * tq + 1]);
    qhi[j] = pack2(acc[4 * tq + 2], acc[4 * tq + 3]);
    klo[j] = pack2(acc[4 * tk], acc[4 * tk + 1]);
    vlo[j] = pack2(acc[4 * tv], acc[4 * tv + 1]);
    asm volatile("" : "+r"(khi[j]), "+r"(qlo[j]), "+r"(qhi[j]), "+r"(klo[j]), "+r"(vlo[j]));
  }
}

template <int ROT> __device__ __forceinline__ void halo_send(const float* acc, uint4* ho, uint32_t tag) {
#pragma unroll
  for (int j = 0; j < 7; j++) {
    uint32_t x[3];
#pragma unroll
    for (int e = 0; e < 3; e++) {
      const int i = 3 * j + e, y = (i % 10 + ROT) % 10, tk = y < 8 ? 8 + y : 18 + y, tv = y < 8 ? 16 + y : 20 + y;
      x[e] = i < 10 ? pack2(acc[4 * tk + 2], acc[4 * tk + 3]) : i < 20 ? movm(pack2(acc[4 * tv + 2], acc[4 * tv + 3])) : 0u;
    }
    asm volatile("st.relaxed.gpu.global.v4.u32 [%0], {%1, %2, %3, %4};" ::"l"(ho + 32 * j), "r"(x[0]), "r"(x[1]), "r"(x[2]), "r"(tag) : "memory");
  }
}

__device__ __forceinline__ void attention(float* acc, uint32_t sb, int b, int par, int w, int lane, uint32_t tag) {
  const int g = lane >> 2, t = lane & 3;
  uint32_t klo[10], khi[10], vlo[10], vhi[10], qlo[10], qhi[10], kpv[10], vpv[10];
  if (w == 3 && b < NCTA - 8) {
    uint4* ho = g_halo + (b * 2 + par) * 224 + lane;
    if (tail_first(b & 7)) halo_send<8>(acc, ho, tag);
    else halo_send<0>(acc, ho, tag);
    TSIF(par == 0, 76);
    pin<120>(acc);
  }
  if (tail_first(b & 7)) pack_qkv<8>(acc, qlo, qhi, klo, khi, vlo, vhi);
  else pack_qkv<0>(acc, qlo, qhi, klo, khi, vlo, vhi);
  const uint32_t xa = sb + OFF_KVX + (par * 3) * 2560 + lane * 16;
  if (w < 3) {
    sts128(xa + w * 2560, khi[0], khi[1], khi[2], khi[3]);
    sts128(xa + w * 2560 + 512, khi[4], khi[5], khi[6], khi[7]);
    sts128(xa + w * 2560 + 1024, khi[8], khi[9], vhi[0], vhi[1]);
    sts128(xa + w * 2560 + 1536, vhi[2], vhi[3], vhi[4], vhi[5]);
    sts128(xa + w * 2560 + 2048, vhi[6], vhi[7], vhi[8], vhi[9]);
  }
  TSIF(par == 0 && w == 1, 64);
#pragma unroll
  for (int j = 0; j < 10; j++) vlo[j] = movm(vlo[j]);
  const bool far0 = 2 * t > g, far1 = 2 * t + 1 > g;
  const uint32_t mfar = (far0 ? 0x0000FFFFu : 0u) | (far1 ? 0xFFFF0000u : 0u);
  float slo[4][2], lg[2][2];
  uint32_t phi[4], plo[4], qml[4], qmh[4];
#pragma unroll
  for (int h = 0; h < 4; h++) {
    const int f = h == 0 ? 0 : h == 1 ? 3 : h == 2 ? 5 : 8, hf = h < 2 ? 2 : 7;
    const bool mine = (h & 1) ? t >= 2 : t < 2;
    qml[h] = mine ? qlo[hf] : 0u;
    qmh[h] = mine ? qhi[hf] : 0u;
    float a[4] = {0.f, 0.f, 0.f, 0.f}, c[4] = {0.f, 0.f, 0.f, 0.f};
    mma16816(a, qlo[f], qhi[f], qlo[f + 1], qhi[f + 1], klo[f], klo[f + 1]);
    mma16816(c, qlo[f], qhi[f], qlo[f + 1], qhi[f + 1], khi[f], khi[f + 1]);
    mma1688(a, qml[h], qmh[h], klo[hf]);
    mma1688(c, qml[h], qmh[h], khi[hf]);
    slo[h][0] = a[0];
    slo[h][1] = a[1];
    lg[h & 1][0] = far0 ? a[2] : c[2];
    lg[h & 1][1] = far1 ? a[3] : c[3];
    if (h & 1) softmax_two(lg, phi[h - 1], phi[h]);
  }
  TSIF(par == 0 && w == 1, 65);
  wg_sync(1 + par);
  TSIF(par == 0 && w == 1, 66);
  const bool nohist = (w == 0) && (b < 8);
  const uint4* hp = g_halo + ((b - 8) * 2 + par) * 224 + lane;
  uint32_t tg[7];
  if (w > 0) {
    const uint4 v0 = lds128(xa + (w - 1) * 2560), v1 = lds128(xa + (w - 1) * 2560 + 512), v2 = lds128(xa + (w - 1) * 2560 + 1024);
    const uint4 v3 = lds128(xa + (w - 1) * 2560 + 1536), v4 = lds128(xa + (w - 1) * 2560 + 2048);
    kpv[0] = v0.x; kpv[1] = v0.y; kpv[2] = v0.z; kpv[3] = v0.w; kpv[4] = v1.x; kpv[5] = v1.y; kpv[6] = v1.z; kpv[7] = v1.w;
    kpv[8] = v2.x; kpv[9] = v2.y; vpv[0] = v2.z; vpv[1] = v2.w; vpv[2] = v3.x; vpv[3] = v3.y; vpv[4] = v3.z; vpv[5] = v3.w;
    vpv[6] = v4.x; vpv[7] = v4.y; vpv[8] = v4.z; vpv[9] = v4.w;
  } else if (nohist) {
#pragma unroll
    for (int j = 0; j < 10; j++) kpv[j] = vpv[j] = 0u;
  } else {
    TSIF(par == 0, 77);
    halo_read(kpv, vpv, tg, hp);
  }
  if (w == 0 && !nohist) {
    int spins = 0;
    while (true) {
      bool ok = true;
#pragma unroll
      for (int j = 0; j < 7; j++) ok = ok && tg[j] == tag;
      if (__all_sync(0xffffffffu, ok) || ++spins > SPIN_LIMIT) break;
      halo_read(kpv, vpv, tg, hp);
    }
    TSIF(par == 0, 79);
  }
#pragma unroll
  for (int h = 0; h < 4; h++) {
    const int f = h == 0 ? 0 : h == 1 ? 3 : h == 2 ? 5 : 8, hf = h < 2 ? 2 : 7;
    float a[4] = {0.f, 0.f, 0.f, 0.f};
    mma16816(a, qlo[f], qhi[f], qlo[f + 1], qhi[f + 1], kpv[f], kpv[f + 1]);
    mma1688(a, qml[h], qmh[h], kpv[hf]);
    const float ninf = __int_as_float(0xff800000);
    lg[h & 1][0] = far0 ? (nohist ? ninf : a[0]) : slo[h][0];
    lg[h & 1][1] = far1 ? (nohist ? ninf : a[1]) : slo[h][1];
    if (h & 1) softmax_two(lg, plo[h - 1], plo[h]);
  }
  TSIF(par == 0 && w <= 1, 67 + w);
  uint32_t ov[20];
#pragma unroll
  for (int hp = 0; hp < 2; hp++) {
    const int hf = hp ? 7 : 2;
    float sh[4] = {0.f, 0.f, 0.f, 0.f}, i0 = 0.f, i1 = 0.f;
#pragma unroll
    for (int e = 0; e < 2; e++) {
      const int h = 2 * hp + e, f = h == 0 ? 0 : h == 1 ? 3 : h == 2 ? 5 : 8;
      const uint32_t a0 = plo[h] & mfar, a2 = plo[h] & ~mfar, a3 = phi[h] & mfar, c1 = phi[h] & ~mfar;
      float sum[4] = {0.f, 0.f, 0.f, 0.f};
      mma1688(sum, plo[h], phi[h], 0x3F803F80u);
      const float r0 = rcp(sum[0]), r1 = rcp(sum[2]);
#pragma unroll
      for (int j = f; j < f + 2; j++) {
        float o[4] = {0.f, 0.f, 0.f, 0.f};
        mma16816(o, a0, 0u, a2, a3, vpv[j], vlo[j]);
        mma1688(o, 0u, c1, vhi[j]);
        ov[2 * j] = pack2(o[0] * r0, o[1] * r0);
        ov[2 * j + 1] = pack2(o[2] * r1, o[3] * r1);
      }
      const bool mine = e ? g >= 4 : g < 4;
      mma16816(sh, a0, 0u, a2, a3, mine ? vpv[hf] : 0u, mine ? vlo[hf] : 0u);
      mma1688(sh, 0u, c1, mine ? vhi[hf] : 0u);
      if (e == 0 || t >= 2) {
        i0 = r0;
        i1 = r1;
      }
    }
    ov[2 * hf] = pack2(sh[0] * i0, sh[1] * i0);
    ov[2 * hf + 1] = pack2(sh[2] * i1, sh[3] * i1);
  }
  TS(32 + 4 * par + w);
  mbar_wait(sb + OFF_BAR + 8 * B_P1, 0);
  const uint32_t oa = sb + OFF_OA + (lane >> 4) * 2048 + (32 * w + 2 * (lane & 15) + par) * 16;
#pragma unroll
  for (int j = 0; j < 5; j++) stsm4(oa + 4096 * j, ov + 4 * j);
  TSIF(par == 0 && w == 0, 120);
  fence_async_smem();
  TSIF(par == 0 && w == 0, 121);
  __syncwarp();
  if (lane == 0) mbar_arrive(sb + OFF_BAR + 8 * B_ATTN);
  TSM(w == 0 || w == 2, 122 + par + (w == 2 ? 3 : 0));
}

struct Maps {
  CUtensorMap x, wm, wt, k, v, y, wo, qm, qt, om, ot, yl, ol;
};

__device__ __forceinline__ void load_stage(uint32_t sb, int kb, int b, const Maps& m) {
  const uint32_t st = sb + (kb & 3) * STAGE_BYTES, bar = sb + OFF_BAR + 8 * (B_FULL1 + (kb & 3));
  const int r = b >> 3, hg = b & 7, slab = kb - KV_KB;
  const bool kv = slab >= 0 && slab < 5;
  const uint32_t kbar = sb + OFF_BAR + 8 * (B_KV + slab), dst = sb + OFF_KVS + slab * KVS_BYTES;
  mbar_expect_tx(bar, STAGE_BYTES);
  if (kv) mbar_expect_tx(kbar, KVS_BYTES);
  tma_3d(st, &m.x, 64 * kb, 64 * r, 0, bar);
  tma_3d(st + ST_W, &m.wm, 80 * hg + (tail_first(hg) ? 16 : 0), 64 * kb, 0, bar);
  tma_3d(st + ST_WT, &m.wt, 80 * hg + (tail_first(hg) ? 0 : 64), 64 * kb, 0, bar);
  if (kv) tma_3d(dst, &m.k, 0, 32 * (b >> 1) - 3, 2 * slab + (b & 1), kbar);
  if (kv) tma_3d(dst + KVS_V, &m.v, 0, 32 * (b >> 1), 2 * slab + (b & 1), kbar);
}

__global__ void __launch_bounds__(NTHR, 1) fused_kernel(const __grid_constant__ Maps m, const Params p) {
  extern __shared__ __align__(1024) uint8_t smem[];
  const uint32_t sb = (uint32_t)__cvta_generic_to_shared(smem);
  const uint32_t bars = sb + OFF_BAR;
  const int tid = threadIdx.x, lane = tid & 31;
  int b = blockIdx.x;
  b = (((b & 63) >> 3) * 2 + (b & 1)) * 8 + (((b < 64 ? 0x6521 : 0x7430) >> (4 * ((b >> 1) & 3))) & 7);
  const int r = b >> 3, hg = b & 7;

  if (tid == T_ISSUE) {
    TSM(true, 0);
    mbar_init(bars + 8 * B_F0, 1);
    fence_async_smem();
    mbar_expect_tx(bars + 8 * B_F0, ST_WT);
    tma_3d(sb, &m.x, 0, 64 * r, 0, bars + 8 * B_F0);
    tma_3d(sb + ST_W, &m.wm, 80 * hg + (tail_first(hg) ? 16 : 0), 0, 0, bars + 8 * B_F0);
#pragma unroll
    for (int i = 0; i < 4; i++) mbar_init(bars + 8 * (B_FULL1 + i), 1);
    fence_async_smem();
    mbar_expect_tx(bars + 8 * B_FULL1, STAGE_BYTES - ST_WT);
    tma_3d(sb + ST_WT, &m.wt, 80 * hg + (tail_first(hg) ? 0 : 64), 0, 0, bars + 8 * B_FULL1);
    load_stage(sb, 1, b, m);
  } else if (tid == T_INIT) {
#pragma unroll
    for (int i = 0; i < B_F0; i++) mbar_init(bars + 8 * i, i < B_GATE ? 8 : i < B_CVD ? 4 : i == B_CVD ? 20 : 1);
    fence_async_smem();
  }
  const int warp = __shfl_sync(0xffffffffu, tid >> 5, 0), wg = warp >> 2, w = warp & 3;
  __syncthreads();

  if (wg == 3) {
    asm volatile("setmaxnreg.dec.sync.aligned.u32 56;");
    if (w == 0) {
      if (lane == 0) {
#pragma unroll 1
        for (int kb = 2; kb < 10; kb++) {
          if (kb >= 4) mbar_wait(bars + 8 * (kb == 7 ? B_E3 : B_EMPTY1 + (kb & 3)), (kb >> 3) & 1);
          TSIF(kb >= 4, 44 + kb);
          load_stage(sb, kb, b, m);
          TSIF(kb == 3, 60);
          if (kb == TRIG_KB) mbar_arrive(bars + 8 * B_LAST);
        }
        mbar_wait(bars + 8 * B_WOP, 0);
        mbar_wait(bars + 8 * WL_TRIG, 0);
        mbar_wait(bars + 8 * B_EPOCH, 0);
        flag_wait(g_cnt + C_W + 32 * hg, (lds32(sb + OFF_EPOCH) + 1) * 16);
        TS(30);
#pragma unroll 1
        for (int j = 0; j < 8; j++) {
          if (j >= 6) mbar_wait(bars + 8 * (B_EMPTY2 + j - 6), 0);
          if (j == 4) mbar_wait(bars + 8 * (RB32 & 2 ? B_ORB : B_ATTN), 0);
          TSIF(j >= 6, 100 + j);
          mbar_expect_tx(bars + 8 * (B_FULL2 + j), j == 0 ? WO_BYTES : j == 5 ? O_BYTES + WO_BYTES + 512 : O_BYTES + WO_BYTES);
          bulk_load(sb + off_w(j), g_WO + (hg * 8 + step_src(hg, j)) * 800, WO_BYTES, bars + 8 * (B_FULL2 + j));
        }
        mbar_wait(bars + 8 * (B_EMPTY2 + 3), 0);
        mbar_expect_tx(bars + 8 * B_QF, O_BYTES);
        tma_2d(sb + OFF_QS, &m.qm, 80 * hg, 128 * r, bars + 8 * B_QF);
        tma_2d(sb + OFF_QT, &m.qt, 80 * hg + 64, 128 * r, bars + 8 * B_QF);
      }
    } else if (w == 1) {
      unsigned epoch = 0;
      if (lane == 0) {
        epoch = atomicAdd(g_cnt + C_LAUNCH, 1u) / NCTA;
        asm volatile("st.shared.u32 [%0], %1;" ::"r"(sb + OFF_EPOCH), "r"(epoch) : "memory");
        mbar_arrive(bars + 8 * B_EPOCH);
        mbar_wait(bars + 8 * B_KVD, 0);
        mbar_expect_tx(bars + 8 * B_HB, 5 * 4096);
#pragma unroll 1
        for (int c = 0; c < 5; c++) {
          if (c == 3) mbar_wait(bars + 8 * B_S3, 0);
          bulk_load(sb + off_ch(c) + U_BYTES, p.ssm_k + (5 * b + c) * SEQ, 4096, bars + 8 * B_HB);
        }
#pragma unroll
        for (int c = 0; c < 4; c++) mbar_expect_tx(bars + 8 * (B_U + c), c < 3 ? U_BYTES : 2 * U_BYTES);
        const uint4* usrc = g_U + 5 * b * U_PITCH;
        mbar_wait(bars + 8 * B_USIG, 0);
        flag_wait(g_cnt + C_PREP + 32 * (b & 15), (epoch + 1) * NCTA);
        TS(23);
#pragma unroll
        for (int c = 0; c < 5; c++) {
          if (c == 3) mbar_wait(bars + 8 * (B_U + 2), 0);
          bulk_load(sb + off_ch(c), usrc + c * U_PITCH, U_BYTES, bars + 8 * (B_U + (c < 3 ? c : 3)));
          TSIF(c == 0 || c == 4, 116 + (c >> 2));
        }
      }
      epoch = __shfl_sync(0xffffffffu, epoch, 0);
      if (lane < 8) {
        const int src = (b & ~7) | step_src(hg, lane);
        mbar_wait(bars + 8 * B_ATTN, 0);
        TS(20);
        bool seen = false;
#pragma unroll 1
        for (int spins = 0; spins < SPIN_LIMIT; spins++) {
          const bool now = !seen && (int)(flag_read(g_cnt + C_O + 32 * src) - (epoch + 1)) >= 0;
          if (now && lane >= 1 && lane < 4) bulk_load(sb + off_o(lane), g_O + src * 1280, O_BYTES, bars + 8 * (B_FULL2 + lane));
          seen = seen || now;
          if (__all_sync(0xff, seen)) break;
        }
        TS(21);
        if (lane == 5) bulk_load(sb + OFF_GATE, g_gate + 128 * r, 512, bars + 8 * (B_FULL2 + 5));
#pragma unroll 1
        for (int j = 4; j < 8; j++) {
          if (lane == j) {
            mbar_wait(bars + 8 * (j < 6 ? B_C34 : B_EMPTY2 + j - 6), 0);
            bulk_load(sb + off_o(j), g_O + src * 1280, O_BYTES, bars + 8 * (B_FULL2 + j));
          }
          __syncwarp(0xff);
        }
        TS(22);
      }
    } else if (w == 2) {
      mbar_wait(bars + 8 * B_PREP, 0);
      flag_signal(g_cnt + C_PREP, 16, lane);
      TS(25);
      if (lane == 0) {
        mbar_arrive(bars + 8 * B_USIG);
        mbar_expect_tx(bars + 8 * B_ORB, (RB32 & 2 ? O_BYTES / 4 : O_BYTES) + 64);
        mbar_wait(bars + 8 * B_GATE, 0);
        publish(g_gate + 16 * b, sb + OFF_GATE + 64 * hg, 64, bars + 8 * B_ORB);
        mbar_wait(bars + 8 * B_ATTN, 0);
        if (RB32 & 2) {
          bulk_store(g_O + b * 1280, sb + OFF_OA, O_BYTES);
          bulk_wait_read();
          tma_2d(sb + OFF_KVX + 10240, &m.ol, 48, b * 160, bars + 8 * B_ORB);
        } else {
          publish(g_O + b * 1280, sb + OFF_OA, O_BYTES, bars + 8 * B_ORB);
        }
        TS(74);
        mbar_wait(bars + 8 * B_ORB, 0);
        flag_bump(g_cnt + C_O + 32 * b);
        TS(26);
        mbar_arrive(bars + 8 * B_OSIG);
      }
    } else {
      if (lane == 0) {
        uint4* dst = g_WO + (hg * 8 + (r >> 1)) * 800 + (r & 1) * 80;
        mbar_wait(bars + 8 * B_S3, 0);
        asm volatile("cp.async.bulk.prefetch.L2.global [%0], 6400;" ::"l"(p.wo + b * 3200) : "memory");
        mbar_wait(bars + 8 * B_P1, 0);
        mbar_wait(bars + 8 * WB_TRIG, 0);
        mbar_expect_tx(bars + 8 * B_WST, WO_BYTES / 2);
        tma_3d(sb + OFF_WA, &m.wo, 0, 40 * r, 5 * hg, bars + 8 * B_WST);
        mbar_wait(bars + 8 * B_WST, 0);
#pragma unroll 1
        for (int n = 0; n < 5; n++) bulk_store(dst + 160 * n, sb + OFF_WA + 1280 * n, 1280);
        bulk_wait_read();
        mbar_expect_tx(bars + 8 * B_WST, WO_BYTES / 2);
#pragma unroll 1
        for (int n = 0; n < 5; n++) bulk_load(sb + OFF_WA + 1280 * n, dst + 160 * n, 1280, bars + 8 * B_WST);
        mbar_wait(bars + 8 * B_WST, 1);
        flag_bump(g_cnt + C_W + 32 * hg);
        mbar_arrive(bars + 8 * B_WOP);
        TS(71);
        mbar_expect_tx(bars + 8 * B_C34, 3 * (RB32 & 1 ? 1024 : U_BYTES));
        mbar_expect_tx(bars + 8 * B_YRB, 2 * (RB32 & 1 ? 1024 : U_BYTES));
#pragma unroll 1
        for (int c = 0; c < 5; c++) {
          mbar_wait(bars + 8 * (B_YST + c), 0);
          if (RB32 & 1) {
            bulk_store(g_U + (5 * b + c) * U_PITCH, sb + off_ch(c), U_BYTES);
            bulk_wait_read();
            tma_2d(sb + off_ch(c), &m.yl, 48, (5 * b + c) * (U_PITCH / 8), bars + 8 * (c < 3 ? B_C34 : B_YRB));
          } else {
            publish(g_U + (5 * b + c) * U_PITCH, sb + off_ch(c), U_BYTES, bars + 8 * (c < 3 ? B_C34 : B_YRB));
          }
        }
        TS(75);
        mbar_wait(bars + 8 * B_C34, 0);
        mbar_wait(bars + 8 * B_YRB, 0);
        flag_bump(g_cnt + C_Y + 32 * (b >> 4));
        TS(27);
        mbar_arrive(bars + 8 * B_YSIG);
        mbar_expect_tx(bars + 8 * B_YFULL, 20480);
        flag_wait(g_cnt + C_Y + 32 * hg, (lds32(sb + OFF_EPOCH) + 1) * 16);
        TS(24);
        tma_2d(sb + OFF_YT, &m.y, 128 * r, 80 * hg, bars + 8 * B_YFULL);
        tma_2d(sb + OFF_YT + 10240, &m.y, 128 * r + 64, 80 * hg, bars + 8 * B_YFULL);
      }
    }
  } else {
    asm volatile("setmaxnreg.inc.sync.aligned.u32 152;");
    if (wg < 2) {
      float acc[120];
#pragma unroll
      for (int i = 0; i < 120; i++) acc[i] = 0.f;
      const uint32_t da = desc_lo(sb + wg * 8192, 16), db = desc_lo(sb + ST_W, 8192), dc = desc_lo(sb + ST_WT, 2048);
      mbar_wait(bars + 8 * B_F0, 0);
      TSIF(w == 0 && wg == 0, 1);
      wg_fence();
#pragma unroll
      for (int k = 0; k < 4; k++) WgSST<192>::mma<HI_SW128, HI_SW128>(acc, da + 2 * k, db + 128 * k, 1);
      wg_commit();
      mbar_wait(bars + 8 * B_FULL1, 0);
      wg_fence();
#pragma unroll
      for (int k = 0; k < 4; k++) WgSST<48>::mma<HI_SW128, HI_SW32>(acc + 96, da + 2 * k, dc + 32 * k, 1);
      wg_commit();
#pragma unroll 1
      for (int kb = 1; kb < 10; kb++) {
        mbar_wait(bars + 8 * (B_FULL1 + (kb & 3)), (kb >> 2) & 1);
        const uint32_t so = (kb & 3) * (STAGE_BYTES >> 4);
        wg_fence();
#pragma unroll
        for (int k = 0; k < 4; k++) {
          WgSST<192>::mma<HI_SW128, HI_SW128>(acc, da + so + 2 * k, db + so + 128 * k, 1);
          WgSST<48>::mma<HI_SW128, HI_SW32>(acc + 96, da + so + 2 * k, dc + so + 32 * k, 1);
        }
        wg_commit();
        wg_wait<1>();
        if (lane == 0) mbar_arrive(bars + 8 * (kb == 4 ? B_E3 : B_EMPTY1 + ((kb - 1) & 3)));
      }
      mbar_wait(bars + 8 * B_EPOCH, 0);
      const uint32_t tag = lds32(sb + OFF_EPOCH) + 1;
      mbar_wait(bars + 8 * B_S3, 0);
      wg_wait<0>();
      pin<120>(acc);
      if (lane == 0) mbar_arrive(bars + 8 * B_P1);
      TSM(w == 0, 3 + wg);
      attention(acc, sb, b, wg, w, lane, tag);
    } else {
      const int tw = tid & 127, chl = 64 * (b & 1) + 8 * w + (lane >> 2);
      uint4* up = g_U + chl * U_PITCH + ((4 * (b >> 1) + (lane & 3)) ^ ((b >> 2) & 1));
      uint2 sw[10];
      uint32_t dv = 0;
      if (lane < 5) dv = __ldg(reinterpret_cast<const unsigned short*>(p.ssm_D) + 5 * b + lane);
#pragma unroll
      for (int i = 0; i < 10; i++) sw[i] = ldg64(reinterpret_cast<const uint2*>(p.shift_k) + chl + 128 * (i >> 1) + 32 * (i & 1));
      uint32_t tab[12];
      uint32_t tt[2];
      fft_tables(tab, tw);
      fft_twiddles(tt, tw);
      uint4 res[10];
#pragma unroll
      for (int i = 0; i < 10; i++) res[i] = make_uint4(0, 0, 0, 0);
#pragma unroll 1
      for (int slab = 0; slab < 5; slab++) {
#pragma unroll
        for (int i = 0; i < 8; i++) res[i] = res[i + 2];
        prep_slab(res + 8, sw, sb, slab, w, lane);
        TSIF(w == 0, 99 + 4 * slab);
#pragma unroll
        for (int i = 0; i < 8; i++) sw[i] = sw[i + 2];
      }
      TSIF(w == 0, 28);
      __syncwarp();
      if (lane == 0) mbar_arrive(bars + 8 * B_KVD + ((res[8].x ^ res[9].x) & p.zero));
      mbar_wait(bars + 8 * B_KVD, 0);
      fft_tables_store(tab, sb, tw);
      mbar_wait(bars + 8 * B_LAST, 0);
#pragma unroll
      for (int i = 0; i < 10; i++) up[(128 * (i >> 1) + 32 * (i & 1)) * U_PITCH] = res[i];
      __syncwarp();
      if (lane == 0) mbar_arrive(bars + 8 * B_PREP);
      TSIF(w == 0, 5);
      mbar_wait(bars + 8 * B_LAST, 0);
      prep_gate(p, sb, b, w, lane);
      __syncwarp();
      if (lane == 0) mbar_arrive(bars + 8 * B_GATE);
      TSIF(w == 0, 72);
      mbar_wait(bars + 8 * B_HB, 0);
      TSIF(w == 0, 2);
      const uint32_t ha = sb + U_BYTES + ((tw >> 3) * 16 + 8 + (tw & 7)) * 16;
      uint4 hv[5];
#pragma unroll
      for (int c = 0; c < 5; c++) hv[c] = lds128(ha + off_ch(c));
      __syncwarp();
#pragma unroll
      for (int c = 0; c < 5; c++) sts128((ha ^ 16) + off_ch(c), hv[c].x, hv[c].y, hv[c].z, hv[c].w);
      asm volatile("st.shared.v2.u32 [%0], {%1, %2};" ::"r"(sb + OFF_TT + 8 * tw), "r"(tt[0]), "r"(tt[1]) : "memory");
      if (tw < 5) asm volatile("st.shared.f32 [%0], %1;" ::"r"(sb + OFF_D + 4 * tw), "f"(bf_lo(dv) * 0.125f) : "memory");
      fence_async_smem();
      __syncwarp();
      if (lane == 0) mbar_arrive(bars + 8 * B_HA);
      TSIF(w == 0, 6);
    }

    FftConst fc;
    TSM(w == 0 && wg == 0, 104);
    mbar_wait(bars + 8 * B_HA, 0);
    fft_matrices(fc, sb, w, lane);
    TSM(w == 0 && wg == 0, 105);
    TSM(w == 0 && wg == 2, 124);
#pragma unroll 1
    for (uint32_t tasks = wg == 0 ? TASK0 : wg == 1 ? TASK1 : TASK2; tasks; tasks >>= 4) {
      const int c = (tasks & 7) - 1;
      conv_channel(fc, sb, c, wg, w, lane);
      if (lane == 0) mbar_arrive(bars + 8 * (B_YST + c));
      TSM(w == 0, 10 + c);
    }

    if (wg < 2) {
      const int g = lane >> 2;
      float acc[40];
#pragma unroll
      for (int i = 0; i < 40; i++) acc[i] = 0.f;
      const uint32_t da = desc_lo(sb + wg * 1024, 2048), db = desc_lo(sb, 2560);
      mbar_wait(bars + 8 * B_ORB, 0);
      mbar_wait(bars + 8 * B_FULL2, 0);
      mbar_wait(bars + 8 * B_CVD, 0);
      TSM(w == 0, 15 + wg);
#pragma unroll 1
      for (int j = 0; j < 8; j++) {
        mbar_wait(bars + 8 * (B_FULL2 + j), 0);
        TSM(w == 0 && wg == 0, 44 + (j < 4 ? j : j + 6));
        const uint32_t oa = da + (off_o(j) >> 4), ob = db + (off_w(j) >> 4);
        wg_fence();
#pragma unroll
        for (int k = 0; k < 5; k++) WgSST<80>::mma<HI_NONE, HI_SW32>(acc, oa + 256 * k, ob + 32 * k, 1);
        wg_commit();
        wg_wait<1>();
        if (j >= 1 && j <= 4 && lane == 0) mbar_arrive(bars + 8 * (B_EMPTY2 + j - 1));
      }
      TSIF(w == 0 && wg == 0, 113);
      const int tr = 64 * wg + 16 * w + (lane & 15);
      const uint32_t fm = sb + OFF_QS + tr * 128, fx = (lane >> 4) ^ (tr & 7);
      const uint32_t ft = sb + OFF_QT + tr * 32 + (((lane >> 4) ^ (tr >> 2)) & 1) * 16;
      const float g0 = __uint_as_float(lds32(sb + OFF_GATE + (64 * wg + 16 * w + g) * 4));
      const float g1 = __uint_as_float(lds32(sb + OFF_GATE + (64 * wg + 16 * w + 8 + g) * 4));
      const uint32_t ga = pack2(g0, g0), gb = pack2(g1, g1);
      const uint32_t na = pack2(1.f - g0, 1.f - g0), nb = pack2(1.f - g1, 1.f - g1);

      uint32_t qf[20];
      mbar_wait(bars + 8 * B_QF, 0);
      TSM(w == 0 && wg == 0, 99);
#pragma unroll
      for (int j = 0; j < 5; j++) ldsm4(qf + 4 * j, j < 4 ? fm + ((fx ^ (2 * j)) << 4) : ft);
#pragma unroll
      for (int i = 0; i < 20; i++) {
        qf[i] = bmul((i & 1) ? gb : ga, qf[i]);
        asm volatile("" : "+r"(qf[i]));
      }

      wg_wait<0>();
      pin<40>(acc);
      TSM(w == 0, 17 + wg);
      uint32_t pb[20];
#pragma unroll
      for (int j = 0; j < 10; j++) {
        pb[2 * j] = bmul(na, pack2(acc[4 * j], acc[4 * j + 1]));
        pb[2 * j + 1] = bmul(nb, pack2(acc[4 * j + 2], acc[4 * j + 3]));
        asm volatile("" : "+r"(pb[2 * j]), "+r"(pb[2 * j + 1]));
      }
      const uint32_t ya = sb + OFF_YT + wg * 10240 + ((lane >> 4) * 8 + (lane & 7)) * 128 +
                          (((2 * w + (((lane >> 3) & 1) ^ wg)) ^ (lane & 7)) << 4);
      mbar_wait(bars + 8 * B_YFULL, 0);
      TSM(w == 0 && wg == 0, 19);
#pragma unroll
      for (int j = 0; j < 5; j++) {
        uint32_t y[4];
        ldsm4t(y, ya + 2048 * j);
#pragma unroll
        for (int i = 0; i < 4; i++)
          qf[4 * j + i] = bfma(qf[4 * j + i], y[i], pb[4 * j + i]);
      }
#pragma unroll
      for (int j = 0; j < 5; j++) stsm4(j < 4 ? fm + ((fx ^ (2 * j)) << 4) : ft, qf + 4 * j);
      fence_async_smem();
      __syncwarp();
      if (lane == 0) {
        const int row = 64 * wg + 16 * w;
        asm volatile("cp.async.bulk.tensor.2d.global.shared::cta.bulk_group [%0, {%2, %3}], [%1];"
                     ::"l"(&m.om), "r"(sb + OFF_QS + row * 128), "r"(80 * hg), "r"(128 * r + row) : "memory");
        asm volatile("cp.async.bulk.tensor.2d.global.shared::cta.bulk_group [%0, {%2, %3}], [%1];"
                     ::"l"(&m.ot), "r"(sb + OFF_QT + row * 32), "r"(80 * hg + 64), "r"(128 * r + row) : "memory");
        asm volatile("cp.async.bulk.commit_group;\ncp.async.bulk.wait_group.read 0;" ::: "memory");
      }
      TSM(w == 0 || w == 3, 40 + 2 * wg + (w & 1));
    }
  }
}

typedef CUresult (*EncodeFn)(CUtensorMap*, CUtensorMapDataType, cuuint32_t, void*, const cuuint64_t*, const cuuint64_t*,
                             const cuuint32_t*, const cuuint32_t*, CUtensorMapInterleave, CUtensorMapSwizzle,
                             CUtensorMapL2promotion, CUtensorMapFloatOOBfill);

void encode(EncodeFn fn, CUtensorMap* tm, const void* base, int rank, const cuuint64_t* dims, const cuuint64_t* strides,
            const cuuint32_t* box, CUtensorMapSwizzle swz) {
  const cuuint32_t ones[3] = {1, 1, 1};
  fn(tm, CU_TENSOR_MAP_DATA_TYPE_BFLOAT16, rank, const_cast<void*>(base), dims, strides, box, ones,
     CU_TENSOR_MAP_INTERLEAVE_NONE, swz, CU_TENSOR_MAP_L2_PROMOTION_L2_128B, CU_TENSOR_MAP_FLOAT_OOB_FILL_NONE);
}

}

extern "C" void kernel_launch(void* const* d_in, const int* in_sizes, int n_in, void* d_out, int out_size) {
  (void)in_sizes; (void)n_in; (void)out_size;
  Params p;
  p.q = (const __nv_bfloat16*)d_in[0];
  p.k = (const __nv_bfloat16*)d_in[1];
  p.v = (const __nv_bfloat16*)d_in[2];
  p.shift_k = (const __nv_bfloat16*)d_in[3];
  p.ssm_k = (const __nv_bfloat16*)d_in[4];
  p.ssm_D = (const __nv_bfloat16*)d_in[5];
  p.wqkv = (const __nv_bfloat16*)d_in[7];
  p.wo = (const __nv_bfloat16*)d_in[8];
  p.gate_w = (const __nv_bfloat16*)d_in[9];
  p.out = (__nv_bfloat16*)d_out;
  p.zero = 0;

  static EncodeFn fn = nullptr;
  static void *yaddr = nullptr, *oaddr = nullptr;
  if (!fn) {
    cudaDriverEntryPointQueryResult qr;
    void* f = nullptr;
    cudaGetDriverEntryPoint("cuTensorMapEncodeTiled", &f, cudaEnableDefault, &qr);
    fn = (EncodeFn)f;
    cudaGetSymbolAddress(&yaddr, g_U);
    cudaGetSymbolAddress(&oaddr, g_O);
    cudaFuncSetAttribute(fused_kernel, cudaFuncAttributeMaxDynamicSharedMemorySize, SMEM_BYTES);
  }
  Maps m;
  {
    const cuuint64_t dims[3] = {640, 1024, 2}, st[2] = {2560, 1280};
    const cuuint32_t box[3] = {64, 64, 2};
    encode(fn, &m.x, p.q, 3, dims, st, box, CU_TENSOR_MAP_SWIZZLE_128B);
  }
  {
    const cuuint64_t dims[3] = {640, 640, 3}, st[2] = {3840, 1280};
    const cuuint32_t box[3] = {64, 64, 3}, boxt[3] = {16, 64, 3};
    encode(fn, &m.wm, p.wqkv, 3, dims, st, box, CU_TENSOR_MAP_SWIZZLE_128B);
    encode(fn, &m.wt, p.wqkv, 3, dims, st, boxt, CU_TENSOR_MAP_SWIZZLE_32B);
  }
  {
    const cuuint64_t dims[3] = {64, 2048, 10}, st[2] = {1280, 128};
    const cuuint32_t boxk[3] = {64, 35, 1}, boxv[3] = {64, 32, 1};
    encode(fn, &m.k, p.k, 3, dims, st, boxk, CU_TENSOR_MAP_SWIZZLE_128B);
    encode(fn, &m.v, p.v, 3, dims, st, boxv, CU_TENSOR_MAP_SWIZZLE_128B);
  }
  {
    const cuuint64_t dims[3] = {16, 640, 40}, st[2] = {1280, 32};
    const cuuint32_t box[3] = {16, 40, 5};
    encode(fn, &m.wo, p.wo, 3, dims, st, box, CU_TENSOR_MAP_SWIZZLE_32B);
  }
  {
    const cuuint64_t dims[2] = {2048, 640}, st[1] = {U_PITCH * 16};
    const cuuint32_t box[2] = {64, 80};
    encode(fn, &m.y, yaddr, 2, dims, st, box, CU_TENSOR_MAP_SWIZZLE_128B);
    const cuuint64_t dl[2] = {64, DIM * U_PITCH / 8}, dol[2] = {64, NCTA * 160}, sl[1] = {128};
    const cuuint32_t bl[2] = {16, 32}, bol[2] = {16, 160};
    encode(fn, &m.yl, yaddr, 2, dl, sl, bl, CU_TENSOR_MAP_SWIZZLE_NONE);
    encode(fn, &m.ol, oaddr, 2, dol, sl, bol, CU_TENSOR_MAP_SWIZZLE_NONE);
  }
  {
    const cuuint64_t dims[2] = {640, 2048}, st[1] = {1280};
    const cuuint32_t bqm[2] = {64, 128}, bqt[2] = {16, 128}, bom[2] = {64, 16}, bot[2] = {16, 16};
    encode(fn, &m.qm, p.q, 2, dims, st, bqm, CU_TENSOR_MAP_SWIZZLE_128B);
    encode(fn, &m.qt, p.q, 2, dims, st, bqt, CU_TENSOR_MAP_SWIZZLE_32B);
    encode(fn, &m.om, p.out, 2, dims, st, bom, CU_TENSOR_MAP_SWIZZLE_128B);
    encode(fn, &m.ot, p.out, 2, dims, st, bot, CU_TENSOR_MAP_SWIZZLE_32B);
  }
  fused_kernel<<<NCTA, NTHR, SMEM_BYTES>>>(m, p);
}
```

```cpp
#include <cuda.h>
#include <cuda_bf16.h>
#include <cuda_runtime.h>
#include <stdint.h>

namespace {

constexpr int SEQ = 2048, DIM = 640, NCTA = 128, NTHR = 512;

#define TRIG_KB 9
#define KV_KB 2
#define DEV_EXIT 0
#define FENCE_LO 0
#define FENCE_HI 0
#define WB_TRIG B_USIG
#define T_ISSUE 256
#define RB32 3
#define Q_SWAP 1
#define Q_SLOT 3
#define T_INIT 448
#define TASK0 0x3
#define TASK1 0x52
#define TASK2 0x41
#define WL_TRIG B_WOP

constexpr uint32_t STAGE_BYTES = 47104, ST_W = 16384, ST_WT = 40960;
constexpr uint32_t O_BYTES = 20480, WO_BYTES = 12800;
constexpr uint32_t OFF_OA = 0;
constexpr uint32_t OFF_QS = Q_SWAP ? 163840 : Q_SLOT * O_BYTES, OFF_QT = OFF_QS + 16384;
constexpr uint32_t OFF_WC = 81920;
constexpr uint32_t OFF_WA = 94720;
constexpr uint32_t OFF_GATE = 145920;
constexpr uint32_t OFF_TT = 146432;
constexpr uint32_t OFF_KVX = 148480;
constexpr uint32_t OFF_CH3 = 163840;
constexpr uint32_t CH_BYTES = 12288, U_BYTES = 4096;
constexpr uint32_t OFF_FT = 225280, OFF_GT = 229376;
constexpr uint32_t OFF_CH0 = 188416;
constexpr uint32_t OFF_KVS = OFF_CH0, KVS_V = 4480, KVS_BYTES = 8576;
constexpr uint32_t OFF_YT = Q_SWAP ? 2 * O_BYTES : 163840;
constexpr uint32_t OFF_BAR = 231936;
constexpr uint32_t SMEM_BYTES = OFF_BAR + 512;

enum : uint32_t {
  B_EMPTY1 = 0, B_S3 = 3, B_E3 = 4, B_EMPTY2 = 5, B_ATTN = 9, B_P1 = 10,
  B_GATE = 11, B_HA = 12, B_KVD = 13, B_PREP = 14, B_YST = 15,
  B_CVD = 20,
  B_FULL2 = 21, B_U = 29, B_KV = 33, B_HB = 38, B_C34 = 39, B_YRB = 40, B_YFULL = 41, B_EPOCH = 42, B_LAST = 43, B_OSIG = 44,
  B_WOP = 45, B_USIG = 46, B_WST = 47, B_QF = 48, B_ORB = 49, B_YSIG = 50,
  B_F0 = 51, B_FULL1 = 52
};
constexpr uint32_t OFF_EPOCH = OFF_BAR + 8 * 58, OFF_D = OFF_BAR + 8 * 60;
__device__ __forceinline__ uint32_t off_o(int j) { return j < 4 ? OFF_OA + j * O_BYTES : j < 6 ? OFF_CH0 + (j - 4) * O_BYTES : OFF_OA + (j - 6) * O_BYTES; }
__device__ __forceinline__ uint32_t off_w(int j) { return j < 4 ? OFF_WA + j * WO_BYTES : j == 4 ? OFF_KVX : j == 5 ? OFF_WC : OFF_WA + (j - 6) * WO_BYTES; }
__device__ __forceinline__ int step_src(int hg, int j) { return j == 0 ? hg : j <= hg ? j - 1 : j; }
__device__ __forceinline__ bool tail_first(int hg) { return (hg & 3) == 3; }
__device__ __forceinline__ uint32_t off_ch(int c) { return (c < 3 ? OFF_CH0 : OFF_CH3 - 3 * CH_BYTES) + c * CH_BYTES; }

#define U_PITCH 264
__device__ __align__(1024) uint4 g_U[DIM * U_PITCH];
__device__ __align__(128) uint4 g_O[NCTA * 1280];
__device__ uint4 g_WO[64 * 800];
__device__ uint4 g_halo[NCTA * 2 * 7 * 32];
__device__ __align__(128) float g_gate[SEQ];
__device__ unsigned g_cnt[32 * (1 + 2 * 16 + 8 + NCTA)];
constexpr int C_LAUNCH = 0, C_PREP = 32, C_Y = 32 * 17, C_W = 32 * 33, C_O = 32 * 41;

#define TSM(cond, slot) do { } while (0)
#define TSIF(cond, slot) do { if (__LINE__ >= FENCE_LO && __LINE__ < FENCE_HI) sched_fence(); } while (0)
__device__ __forceinline__ void sched_fence() {
  asm volatile("{\n.reg .pred p;\n.reg .u32 c;\nmov.u32 c, %%clock;\nsetp.eq.u32 p, c, 0;\n@p st.shared.u32 [%0], c;\n}"
               ::"r"(1024 + OFF_EPOCH + 4) : "memory");
}
#define TS(slot) TSIF(true, slot)

struct Params {
  const __nv_bfloat16 *q, *k, *v, *shift_k, *ssm_k, *ssm_D, *wqkv, *wo, *gate_w;
  __nv_bfloat16* out;
  uint32_t zero;
};

constexpr int SPIN_LIMIT = 1 << 17;

__device__ __forceinline__ void mbar_init(uint32_t bar, uint32_t count) {
  asm volatile("mbarrier.init.shared::cta.b64 [%0], %1;" ::"r"(bar), "r"(count) : "memory");
}
__device__ __forceinline__ void mbar_expect_tx(uint32_t bar, uint32_t bytes) {
  asm volatile("mbarrier.arrive.expect_tx.shared::cta.b64 _, [%0], %1;" ::"r"(bar), "r"(bytes) : "memory");
}
__device__ __forceinline__ void mbar_arrive(uint32_t bar) {
  asm volatile("mbarrier.arrive.shared::cta.b64 _, [%0];" ::"r"(bar) : "memory");
}
__device__ __forceinline__ void mbar_wait(uint32_t bar, uint32_t parity) {
  uint32_t ok;
  int spins = 0;
  do {
      asm volatile("{\n.reg .pred p;\nmbarrier.try_wait.parity.shared::cta.b64 p, [%1], %2;\nselp.b32 %0, 1, 0, p;\n}"
                   : "=r"(ok) : "r"(bar), "r"(parity) : "memory");
    if (++spins > SPIN_LIMIT) break;
  } while (!ok);
}
__device__ __forceinline__ unsigned flag_read(const unsigned* p) {
  unsigned v;
  asm volatile("ld.relaxed.gpu.global.u32 %0, [%1];" : "=r"(v) : "l"(p) : "memory");
  return v;
}
__device__ __forceinline__ void flag_poll(const unsigned* p, unsigned target) {
  unsigned v;
  int spins = 0;
  do {
    asm volatile("ld.relaxed.gpu.global.u32 %0, [%1];" : "=r"(v) : "l"(p) : "memory");
    if (++spins > SPIN_LIMIT) break;
  } while ((int)(v - target) < 0);
}
__device__ __forceinline__ void flag_wait(const unsigned* p, unsigned target) {
  flag_poll(p, target);
}
__device__ __forceinline__ void flag_signal(unsigned* p, int n, int lane) {
  if (lane == 0) asm volatile("fence.release.gpu;" ::: "memory");
  __syncwarp();
  if (lane < n) asm volatile("red.relaxed.gpu.global.add.u32 [%0], 1;" ::"l"(p + 32 * lane) : "memory");
}
__device__ __forceinline__ void flag_bump(unsigned* p) {
  asm volatile("red.relaxed.gpu.global.add.u32 [%0], 1;" ::"l"(p) : "memory");
}
__device__ __forceinline__ void fence_async_smem() { asm volatile("fence.proxy.async.shared::cta;" ::: "memory"); }
__device__ __forceinline__ void wg_sync(int id) { asm volatile("bar.sync %0, 128;" ::"r"(id) : "memory"); }

__device__ __forceinline__ void tma_2d(uint32_t dst, const CUtensorMap* tm, int c0, int c1, uint32_t bar) {
  asm volatile("cp.async.bulk.tensor.2d.shared::cluster.global.mbarrier::complete_tx::bytes [%0], [%1, {%3, %4}], [%2];"
               ::"r"(dst), "l"(tm), "r"(bar), "r"(c0), "r"(c1) : "memory");
}
__device__ __forceinline__ void tma_3d(uint32_t dst, const CUtensorMap* tm, int c0, int c1, int c2, uint32_t bar) {
  asm volatile("cp.async.bulk.tensor.3d.shared::cluster.global.mbarrier::complete_tx::bytes [%0], [%1, {%3, %4, %5}], [%2];"
               ::"r"(dst), "l"(tm), "r"(bar), "r"(c0), "r"(c1), "r"(c2) : "memory");
}
__device__ __forceinline__ void bulk_load(uint32_t dst, const void* src, uint32_t bytes, uint32_t bar) {
  asm volatile("cp.async.bulk.shared::cluster.global.mbarrier::complete_tx::bytes [%0], [%1], %2, [%3];"
               ::"r"(dst), "l"(src), "r"(bytes), "r"(bar) : "memory");
}
__device__ __forceinline__ void bulk_store(void* dst, uint32_t src, uint32_t bytes) {
  asm volatile("cp.async.bulk.global.shared::cta.bulk_group [%0], [%1], %2;" ::"l"(dst), "r"(src), "r"(bytes) : "memory");
}
__device__ __forceinline__ void bulk_wait_read() {
  asm volatile("cp.async.bulk.commit_group;\ncp.async.bulk.wait_group.read 0;" ::: "memory");
}

__device__ __forceinline__ void publish(void* dst, uint32_t src, uint32_t bytes, uint32_t bar) {
  bulk_store(dst, src, bytes);
  bulk_wait_read();
  bulk_load(src, dst, bytes, bar);
}

__device__ __forceinline__ void wg_fence() { asm volatile("wgmma.fence.sync.aligned;" ::: "memory"); }
__device__ __forceinline__ void wg_commit() { asm volatile("wgmma.commit_group.sync.aligned;" ::: "memory"); }
template <int N> __device__ __forceinline__ void wg_wait() { asm volatile("wgmma.wait_group.sync.aligned %0;" ::"n"(N) : "memory"); }
__device__ __forceinline__ uint32_t desc_lo(uint32_t addr, uint32_t lbo) { return ((addr & 0x3FFFF) >> 4) | ((lbo >> 4) << 16); }
constexpr uint32_t desc_hi(uint32_t sbo, uint32_t swz) { return (sbo >> 4) | (swz << 30); }
constexpr uint32_t HI_SW128 = desc_hi(1024, 1), HI_SW64 = desc_hi(512, 2), HI_SW32 = desc_hi(256, 3), HI_NONE = desc_hi(128, 0);
template <int N> __device__ __forceinline__ void pin(float* d) {
#pragma unroll
  for (int i = 0; i < N; i++) asm volatile("" : "+f"(d[i])::"memory");
}

__device__ __forceinline__ uint32_t lds32(uint32_t a) {
  uint32_t v;
  asm volatile("ld.volatile.shared.u32 %0, [%1];" : "=r"(v) : "r"(a) : "memory");
  return v;
}
__device__ __forceinline__ uint2 ldg64(const void* a) {
  uint2 v;
  asm volatile("ld.global.nc.v2.u32 {%0, %1}, [%2];" : "=r"(v.x), "=r"(v.y) : "l"(a) : "memory");
  return v;
}
__device__ __forceinline__ void ldsm4(uint32_t* r, uint32_t a) {
  asm volatile("ldmatrix.sync.aligned.m8n8.x4.shared.b16 {%0, %1, %2, %3}, [%4];"
               : "=r"(r[0]), "=r"(r[1]), "=r"(r[2]), "=r"(r[3]) : "r"(a) : "memory");
}
__device__ __forceinline__ void ldsm4t(uint32_t* r, uint32_t a) {
  asm volatile("ldmatrix.sync.aligned.m8n8.x4.trans.shared.b16 {%0, %1, %2, %3}, [%4];"
               : "=r"(r[0]), "=r"(r[1]), "=r"(r[2]), "=r"(r[3]) : "r"(a) : "memory");
}
__device__ __forceinline__ uint2 lds64(uint32_t a) {
  uint2 v;
  asm volatile("ld.shared.v2.u32 {%0, %1}, [%2];" : "=r"(v.x), "=r"(v.y) : "r"(a) : "memory");
  return v;
}
__device__ __forceinline__ uint4 lds128(uint32_t a) {
  uint4 v;
  asm volatile("ld.shared.v4.u32 {%0, %1, %2, %3}, [%4];" : "=r"(v.x), "=r"(v.y), "=r"(v.z), "=r"(v.w) : "r"(a) : "memory");
  return v;
}
__device__ __forceinline__ void sts128(uint32_t a, uint32_t x, uint32_t y, uint32_t z, uint32_t w) {
  asm volatile("st.shared.v4.u32 [%0], {%1, %2, %3, %4};" ::"r"(a), "r"(x), "r"(y), "r"(z), "r"(w) : "memory");
}
__device__ __forceinline__ void stsm4(uint32_t a, const uint32_t* r) {
  asm volatile("stmatrix.sync.aligned.m8n8.x4.shared.b16 [%0], {%1, %2, %3, %4};" ::"r"(a), "r"(r[0]), "r"(r[1]), "r"(r[2]), "r"(r[3]) : "memory");
}
__device__ __forceinline__ uint32_t pack2(float lo, float hi) {
  uint32_t r;
  asm("cvt.rn.bf16x2.f32 %0, %1, %2;" : "=r"(r) : "f"(hi), "f"(lo));
  return r;
}
__device__ __forceinline__ uint32_t movm(uint32_t a) {
  uint32_t d;
  asm volatile("movmatrix.sync.aligned.m8n8.trans.b16 %0, %1;" : "=r"(d) : "r"(a));
  return d;
}
__device__ __forceinline__ uint32_t bmul(uint32_t a, uint32_t b) {
  uint32_t d;
  asm("mul.rn.bf16x2 %0, %1, %2;" : "=r"(d) : "r"(a), "r"(b));
  return d;
}
__device__ __forceinline__ uint32_t badd(uint32_t a, uint32_t b) {
  uint32_t d;
  asm("add.rn.bf16x2 %0, %1, %2;" : "=r"(d) : "r"(a), "r"(b));
  return d;
}
__device__ __forceinline__ uint32_t bfma(uint32_t a, uint32_t b, uint32_t c) {
  uint32_t d;
  asm("fma.rn.bf16x2 %0, %1, %2, %3;" : "=r"(d) : "r"(a), "r"(b), "r"(c));
  return d;
}
__device__ __forceinline__ float bf_lo(uint32_t x) { return __uint_as_float(x << 16); }
__device__ __forceinline__ float bf_hi(uint32_t x) { return __uint_as_float(x & 0xFFFF0000u); }
__device__ __forceinline__ float ex2(float x) {
  float y;
  asm("ex2.approx.ftz.f32 %0, %1;" : "=f"(y) : "f"(x));
  return y;
}
__device__ __forceinline__ float rcp(float x) {
  float y;
  asm("rcp.approx.ftz.f32 %0, %1;" : "=f"(y) : "f"(x));
  return y;
}
__device__ __forceinline__ void mma16816(float* d, uint32_t a0, uint32_t a1, uint32_t a2, uint32_t a3, uint32_t b0, uint32_t b1) {
  asm volatile("mma.sync.aligned.m16n8k16.row.col.f32.bf16.bf16.f32 {%0, %1, %2, %3}, {%4, %5, %6, %7}, {%8, %9}, {%0, %1, %2, %3};"
               : "+f"(d[0]), "+f"(d[1]), "+f"(d[2]), "+f"(d[3])
               : "r"(a0), "r"(a1), "r"(a2), "r"(a3), "r"(b0), "r"(b1));
}
__device__ __forceinline__ void mma1688(float* d, uint32_t a0, uint32_t a1, uint32_t b0) {
  asm volatile("mma.sync.aligned.m16n8k8.row.col.f32.bf16.bf16.f32 {%0, %1, %2, %3}, {%4, %5}, {%6}, {%0, %1, %2, %3};"
               : "+f"(d[0]), "+f"(d[1]), "+f"(d[2]), "+f"(d[3])
               : "r"(a0), "r"(a1), "r"(b0));
}

template <int N> struct WgRS;
template <int N> struct WgSST;
template <> struct WgRS<32> {
  template <uint32_t HB>
  static __device__ __forceinline__ void mma(float* d, const uint32_t* a, uint32_t db) {
    asm volatile("{\n.reg .pred p;\n.reg .b64 db;\nsetp.ne.b32 p, %22, 0;\n"
      "mov.b64 db, {%20, %21};\n"
      "wgmma.mma_async.sync.aligned.m64n32k16.f32.bf16.bf16 {"
      "%0, %1, %2, %3, %4, %5, %6, %7, %8, %9, %10, %11, %12, %13, %14, %15"
      "}, {%16, %17, %18, %19}, db, p, 1, 1, 1;\n}\n"
      : "+f"(d[0]), "+f"(d[1]), "+f"(d[2]), "+f"(d[3]), "+f"(d[4]), "+f"(d[5]), "+f"(d[6]), "+f"(d[7]),
        "+f"(d[8]), "+f"(d[9]), "+f"(d[10]), "+f"(d[11]), "+f"(d[12]), "+f"(d[13]), "+f"(d[14]), "+f"(d[15])
      : "r"(a[0]), "r"(a[1]), "r"(a[2]), "r"(a[3]), "r"(db), "n"(HB), "n"(1));
  }
  template <uint32_t HB>
  static __device__ __forceinline__ void set(float* d, const uint32_t* a, uint32_t db) {
    asm volatile("{\n.reg .pred p;\n.reg .b64 db;\nsetp.ne.b32 p, %22, 0;\n"
      "mov.b64 db, {%20, %21};\n"
      "wgmma.mma_async.sync.aligned.m64n32k16.f32.bf16.bf16 {"
      "%0, %1, %2, %3, %4, %5, %6, %7, %8, %9, %10, %11, %12, %13, %14, %15"
      "}, {%16, %17, %18, %19}, db, p, 1, 1, 1;\n}\n"
      : "=f"(d[0]), "=f"(d[1]), "=f"(d[2]), "=f"(d[3]), "=f"(d[4]), "=f"(d[5]), "=f"(d[6]), "=f"(d[7]),
        "=f"(d[8]), "=f"(d[9]), "=f"(d[10]), "=f"(d[11]), "=f"(d[12]), "=f"(d[13]), "=f"(d[14]), "=f"(d[15])
      : "r"(a[0]), "r"(a[1]), "r"(a[2]), "r"(a[3]), "r"(db), "n"(HB), "n"(0));
  }
};
template <> struct WgRS<64> {
  template <uint32_t HB>
  static __device__ __forceinline__ void mma(float* d, const uint32_t* a, uint32_t db) {
    asm volatile("{\n.reg .pred p;\n.reg .b64 db;\nsetp.ne.b32 p, %38, 0;\n"
      "mov.b64 db, {%36, %37};\n"
      "wgmma.mma_async.sync.aligned.m64n64k16.f32.bf16.bf16 {"
      "%0, %1, %2, %3, %4, %5, %6, %7, %8, %9, %10, %11, %12, %13, %14, %15, "
      "%16, %17, %18, %19, %20, %21, %22, %23, %24, %25, %26, %27, %28, %29, %30, %31"
      "}, {%32, %33, %34, %35}, db, p, 1, 1, 1;\n}\n"
      : "+f"(d[0]), "+f"(d[1]), "+f"(d[2]), "+f"(d[3]), "+f"(d[4]), "+f"(d[5]), "+f"(d[6]), "+f"(d[7]),
        "+f"(d[8]), "+f"(d[9]), "+f"(d[10]), "+f"(d[11]), "+f"(d[12]), "+f"(d[13]), "+f"(d[14]), "+f"(d[15]),
        "+f"(d[16]), "+f"(d[17]), "+f"(d[18]), "+f"(d[19]), "+f"(d[20]), "+f"(d[21]), "+f"(d[22]), "+f"(d[23]),
        "+f"(d[24]), "+f"(d[25]), "+f"(d[26]), "+f"(d[27]), "+f"(d[28]), "+f"(d[29]), "+f"(d[30]), "+f"(d[31])
      : "r"(a[0]), "r"(a[1]), "r"(a[2]), "r"(a[3]), "r"(db), "n"(HB), "n"(1));
  }
  template <uint32_t HB>
  static __device__ __forceinline__ void set(float* d, const uint32_t* a, uint32_t db) {
    asm volatile("{\n.reg .pred p;\n.reg .b64 db;\nsetp.ne.b32 p, %38, 0;\n"
      "mov.b64 db, {%36, %37};\n"
      "wgmma.mma_async.sync.aligned.m64n64k16.f32.bf16.bf16 {"
      "%0, %1, %2, %3, %4, %5, %6, %7, %8, %9, %10, %11, %12, %13, %14, %15, "
      "%16, %17, %18, %19, %20, %21, %22, %23, %24, %25, %26, %27, %28, %29, %30, %31"
      "}, {%32, %33, %34, %35}, db, p, 1, 1, 1;\n}\n"
      : "=f"(d[0]), "=f"(d[1]), "=f"(d[2]), "=f"(d[3]), "=f"(d[4]), "=f"(d[5]), "=f"(d[6]), "=f"(d[7]),
        "=f"(d[8]), "=f"(d[9]), "=f"(d[10]), "=f"(d[11]), "=f"(d[12]), "=f"(d[13]), "=f"(d[14]), "=f"(d[15]),
        "=f"(d[16]), "=f"(d[17]), "=f"(d[18]), "=f"(d[19]), "=f"(d[20]), "=f"(d[21]), "=f"(d[22]), "=f"(d[23]),
        "=f"(d[24]), "=f"(d[25]), "=f"(d[26]), "=f"(d[27]), "=f"(d[28]), "=f"(d[29]), "=f"(d[30]), "=f"(d[31])
      : "r"(a[0]), "r"(a[1]), "r"(a[2]), "r"(a[3]), "r"(db), "n"(HB), "n"(0));
  }
};
template <> struct WgSST<48> {
  template <uint32_t HA, uint32_t HB>
  static __device__ __forceinline__ void mma(float* d, uint32_t da, uint32_t db, int sc) {
    asm volatile("{\n.reg .pred p;\n.reg .b64 da, db;\nsetp.ne.b32 p, %28, 0;\n"
      "mov.b64 da, {%24, %25};\nmov.b64 db, {%26, %27};\n"
      "wgmma.mma_async.sync.aligned.m64n48k16.f32.bf16.bf16 {"
      "%0, %1, %2, %3, %4, %5, %6, %7, %8, %9, %10, %11, %12, %13, %14, %15, "
      "%16, %17, %18, %19, %20, %21, %22, %23"
      "}, da, db, p, 1, 1, 0, 1;\n}\n"
      : "+f"(d[0]), "+f"(d[1]), "+f"(d[2]), "+f"(d[3]), "+f"(d[4]), "+f"(d[5]), "+f"(d[6]), "+f"(d[7]),
        "+f"(d[8]), "+f"(d[9]), "+f"(d[10]), "+f"(d[11]), "+f"(d[12]), "+f"(d[13]), "+f"(d[14]), "+f"(d[15]),
        "+f"(d[16]), "+f"(d[17]), "+f"(d[18]), "+f"(d[19]), "+f"(d[20]), "+f"(d[21]), "+f"(d[22]), "+f"(d[23])
      : "r"(da), "n"(HA), "r"(db), "n"(HB), "r"(sc));
  }
};
template <> struct WgSST<80> {
  template <uint32_t HA, uint32_t HB>
  static __device__ __forceinline__ void mma(float* d, uint32_t da, uint32_t db, int sc) {
    asm volatile("{\n.reg .pred p;\n.reg .b64 da, db;\nsetp.ne.b32 p, %44, 0;\n"
      "mov.b64 da, {%40, %41};\nmov.b64 db, {%42, %43};\n"
      "wgmma.mma_async.sync.aligned.m64n80k16.f32.bf16.bf16 {"
      "%0, %1, %2, %3, %4, %5, %6, %7, %8, %9, %10, %11, %12, %13, %14, %15, "
      "%16, %17, %18, %19, %20, %21, %22, %23, %24, %25, %26, %27, %28, %29, %30, %31, "
      "%32, %33, %34, %35, %36, %37, %38, %39"
      "}, da, db, p, 1, 1, 0, 1;\n}\n"
      : "+f"(d[0]), "+f"(d[1]), "+f"(d[2]), "+f"(d[3]), "+f"(d[4]), "+f"(d[5]), "+f"(d[6]), "+f"(d[7]),
        "+f"(d[8]), "+f"(d[9]), "+f"(d[10]), "+f"(d[11]), "+f"(d[12]), "+f"(d[13]), "+f"(d[14]), "+f"(d[15]),
        "+f"(d[16]), "+f"(d[17]), "+f"(d[18]), "+f"(d[19]), "+f"(d[20]), "+f"(d[21]), "+f"(d[22]), "+f"(d[23]),
        "+f"(d[24]), "+f"(d[25]), "+f"(d[26]), "+f"(d[27]), "+f"(d[28]), "+f"(d[29]), "+f"(d[30]), "+f"(d[31]),
        "+f"(d[32]), "+f"(d[33]), "+f"(d[34]), "+f"(d[35]), "+f"(d[36]), "+f"(d[37]), "+f"(d[38]), "+f"(d[39])
      : "r"(da), "n"(HA), "r"(db), "n"(HB), "r"(sc));
  }
};
template <> struct WgSST<192> {
  template <uint32_t HA, uint32_t HB>
  static __device__ __forceinline__ void mma(float* d, uint32_t da, uint32_t db, int sc) {
    asm volatile("{\n.reg .pred p;\n.reg .b64 da, db;\nsetp.ne.b32 p, %100, 0;\n"
      "mov.b64 da, {%96, %97};\nmov.b64 db, {%98, %99};\n"
      "wgmma.mma_async.sync.aligned.m64n192k16.f32.bf16.bf16 {"
      "%0, %1, %2, %3, %4, %5, %6, %7, %8, %9, %10, %11, %12, %13, %14, %15, "
      "%16, %17, %18, %19, %20, %21, %22, %23, %24, %25, %26, %27, %28, %29, %30, %31, "
      "%32, %33, %34, %35, %36, %37, %38, %39, %40, %41, %42, %43, %44, %45, %46, %47, "
      "%48, %49, %50, %51, %52, %53, %54, %55, %56, %57, %58, %59, %60, %61, %62, %63, "
      "%64, %65, %66, %67, %68, %69, %70, %71, %72, %73, %74, %75, %76, %77, %78, %79, "
      "%80, %81, %82, %83, %84, %85, %86, %87, %88, %89, %90, %91, %92, %93, %94, %95"
      "}, da, db, p, 1, 1, 0, 1;\n}\n"
      : "+f"(d[0]), "+f"(d[1]), "+f"(d[2]), "+f"(d[3]), "+f"(d[4]), "+f"(d[5]), "+f"(d[6]), "+f"(d[7]),
        "+f"(d[8]), "+f"(d[9]), "+f"(d[10]), "+f"(d[11]), "+f"(d[12]), "+f"(d[13]), "+f"(d[14]), "+f"(d[15]),
        "+f"(d[16]), "+f"(d[17]), "+f"(d[18]), "+f"(d[19]), "+f"(d[20]), "+f"(d[21]), "+f"(d[22]), "+f"(d[23]),
        "+f"(d[24]), "+f"(d[25]), "+f"(d[26]), "+f"(d[27]), "+f"(d[28]), "+f"(d[29]), "+f"(d[30]), "+f"(d[31]),
        "+f"(d[32]), "+f"(d[33]), "+f"(d[34]), "+f"(d[35]), "+f"(d[36]), "+f"(d[37]), "+f"(d[38]), "+f"(d[39]),
        "+f"(d[40]), "+f"(d[41]), "+f"(d[42]), "+f"(d[43]), "+f"(d[44]), "+f"(d[45]), "+f"(d[46]), "+f"(d[47]),
        "+f"(d[48]), "+f"(d[49]), "+f"(d[50]), "+f"(d[51]), "+f"(d[52]), "+f"(d[53]), "+f"(d[54]), "+f"(d[55]),
        "+f"(d[56]), "+f"(d[57]), "+f"(d[58]), "+f"(d[59]), "+f"(d[60]), "+f"(d[61]), "+f"(d[62]), "+f"(d[63]),
        "+f"(d[64]), "+f"(d[65]), "+f"(d[66]), "+f"(d[67]), "+f"(d[68]), "+f"(d[69]), "+f"(d[70]), "+f"(d[71]),
        "+f"(d[72]), "+f"(d[73]), "+f"(d[74]), "+f"(d[75]), "+f"(d[76]), "+f"(d[77]), "+f"(d[78]), "+f"(d[79]),
        "+f"(d[80]), "+f"(d[81]), "+f"(d[82]), "+f"(d[83]), "+f"(d[84]), "+f"(d[85]), "+f"(d[86]), "+f"(d[87]),
        "+f"(d[88]), "+f"(d[89]), "+f"(d[90]), "+f"(d[91]), "+f"(d[92]), "+f"(d[93]), "+f"(d[94]), "+f"(d[95])
      : "r"(da), "n"(HA), "r"(db), "n"(HB), "r"(sc));
  }
};

struct FftConst {
  uint32_t f[2][4], fi[4][4];
  uint32_t ta[2][2], tb[2][2];
};
__device__ __forceinline__ void cis(int m, float scale, float& c, float& s) {
  const float a = (float)m * (-6.283185307179586f * scale);
  c = __cosf(a);
  s = __sinf(a);
}
__device__ __forceinline__ void fft_tables(uint32_t (&v)[12], int tw) {
  const int row = tw >> 2, ch = tw & 3;
#pragma unroll
  for (int i = 0; i < 4; i++) {
    float c[2], s[2], x[2];
#pragma unroll
    for (int e = 0; e < 2; e++) {
      cis((((32 * (8 * ch + 2 * i + e) + 15) * (4 * row - 63) + 2048) & 4095) - 2048, 1.f / 4096, c[e], s[e]);
      float gc, gs;
      cis((((row & 15) * (8 * (ch & 1) + 2 * i + e) + 8) & 15) - 8, 1.f / 16, gc, gs);
      x[e] = (row >> 4) == (ch >> 1) ? gc : (ch >> 1) ? gs : -gs;
    }
    v[i] = pack2(c[0] * 0.125f, c[1] * 0.125f);
    v[4 + i] = pack2(s[0] * 0.125f, s[1] * 0.125f);
    v[8 + i] = pack2(x[0], x[1]);
  }
#pragma unroll
  for (int i = 0; i < 12; i++) asm volatile("" : "+r"(v[i]));
}
__device__ __forceinline__ void fft_tables_store(const uint32_t (&v)[12], uint32_t sb, int tw) {
  const int row = tw >> 2;
  const uint32_t x = ((tw ^ (row >> 1)) & 3) << 4, a = sb + OFF_FT + (16 * (row >> 3) + (row & 7)) * 64 + x;
  sts128(a, v[0], v[1], v[2], v[3]);
  sts128(a + 512, v[4], v[5], v[6], v[7]);
  sts128(sb + OFF_GT + row * 64 + x, v[8], v[9], v[10], v[11]);
}
__device__ __forceinline__ void fft_twiddles(uint32_t (&v)[2], int tw) {
  float a[2], s[2];
#pragma unroll
  for (int i = 0; i < 2; i++) {
    float c;
    cis((2 * (2 * (tw & 3) + i) - 15) * (4 * (tw >> 2) - 63), 1.f / 4096, c, s[i]);
    a[i] = __fdividef(-s[i], 1.f + c);
  }
  v[0] = pack2(a[0], a[1]);
  v[1] = pack2(s[0], s[1]);
  asm volatile("" : "+r"(v[0]), "+r"(v[1]));
}
__device__ __forceinline__ void fft_matrices(FftConst& k, uint32_t sb, int w, int lane) {
  const uint32_t x = (lane >> 1) & 3;
  const uint2 t0 = lds64(sb + OFF_TT + 256 * w + 8 * lane), t1 = lds64(sb + OFF_TT + 256 * w + 8 * (lane ^ 3));
  k.ta[0][0] = t0.x;
  k.tb[0][0] = t0.y;
  k.ta[1][1] = __byte_perm(t1.x, 0, 0x1032);
  k.tb[1][1] = __byte_perm(t1.y, 0, 0x1032);
#pragma unroll
  for (int j = 0; j < 2; j++) {
    k.ta[1 - j][j] = k.ta[j][j] ^ 0x80008000u;
    k.tb[1 - j][j] = k.tb[j][j] ^ 0x80008000u;
    asm volatile("" : "+r"(k.ta[0][j]), "+r"(k.tb[0][j]), "+r"(k.ta[1][j]), "+r"(k.tb[1][j]));
  }
#pragma unroll
  for (int i = 0; i < 2; i++) {
    ldsm4(k.f[i], sb + OFF_FT + (16 * w + (lane & 15)) * 64 + (((2 * i + (lane >> 4)) ^ x) << 4));
    ldsm4t(k.fi[i], sb + OFF_FT + (32 * i + lane) * 64 + ((w ^ x) << 4));
#pragma unroll
    for (int j = 0; j < 4; j++) {
      k.fi[2 + i][j] = (j & 1) ? k.fi[i][j - 1] ^ 0x80008000u : k.fi[i][j + 1];
      asm volatile("" : "+r"(k.fi[2 + i][j]));
    }
  }
}
__device__ __forceinline__ void rot(uint32_t& x, uint32_t& y, uint32_t a, uint32_t b) {
  x = bfma(a, y, x);
  y = bfma(b, x, y);
  x = bfma(a, y, x);
}
__device__ __forceinline__ void twiddle_fwd(uint32_t (&a)[4][4], float* d, const FftConst& k) {
#pragma unroll
  for (int q = 0; q < 4; q++)
#pragma unroll
    for (int j = 0; j < 2; j++) {
      const float* x = d + 8 * q + 4 * j;
      uint32_t re = pack2(x[0], x[1]), im = pack2(x[2], x[3]);
      rot(re, im, k.ta[0][j], k.tb[0][j]);
      a[q & 2][2 * j + (q & 1)] = re;
      a[(q & 2) + 1][2 * j + (q & 1)] = im;
    }
}
__device__ __forceinline__ void g_step(float* d, const uint32_t (&a)[4][4], uint32_t dre, uint32_t dim) {
  WgRS<32>::set<HI_SW64>(d, a[0], dre);
  WgRS<32>::set<HI_SW64>(d + 16, a[2], dre);
  WgRS<32>::mma<HI_SW64>(d, a[1], dim);
  WgRS<32>::mma<HI_SW64>(d + 16, a[3], dim);
  wg_commit();
}

__device__ __forceinline__ void products(uint32_t (&a)[4][4], const float* H, const float* U, int p) {
#pragma unroll
  for (int j = 0; j < 2; j++)
#pragma unroll
    for (int m = 2 * p; m < 2 * p + 2; m++) {
      float pr[2], pi[2];
#pragma unroll
      for (int x = 0; x < 2; x++)
#pragma unroll
        for (int q = 0; q <= m; q++) {
          const int ih = 16 * (q >> 1) + 2 * (q & 1) + 4 * j + x, iu = 16 * ((m - q) >> 1) + 2 * ((m - q) & 1) + 4 * j + x;
          pr[x] = q ? fmaf(H[ih], U[iu], pr[x]) : H[ih] * U[iu];
          pi[x] = q ? fmaf(H[ih], U[iu + 8], pi[x]) : H[ih] * U[iu + 8];
          pr[x] = fmaf(-H[ih + 8], U[iu + 8], pr[x]);
          pi[x] = fmaf(H[ih + 8], U[iu], pi[x]);
        }
      a[m & 2][2 * j + (m & 1)] = pack2(pr[0], pr[1]);
      a[(m & 2) + 1][2 * j + (m & 1)] = pack2(pi[0], pi[1]);
    }
}

__device__ __forceinline__ void conv_channel(const FftConst& k, uint32_t sb, int c, int wg, int w, int lane) {
  const uint32_t cb = sb + off_ch(c), bars = sb + OFF_BAR;
  const uint32_t du = desc_lo(cb, 1024), dg = desc_lo(sb + OFF_GT, 16), dz = desc_lo(cb + U_BYTES, 16);
  float U[32], H[32];
  uint32_t a[4][4], e[4][4];
  const float dv = __uint_as_float(lds32(sb + OFF_D + 4 * c));
  wg_fence();
  WgRS<64>::set<HI_SW32>(H, k.f[0], du + 256);
  WgRS<64>::mma<HI_SW32>(H, k.f[1], du + 256 + 32);
  wg_commit();
  wg_wait<0>();
  pin<32>(H);
  twiddle_fwd(a, H, k);
  mbar_wait(bars + 8 * (B_U + (c < 3 ? c : 3)), 0);
  TSM(w == 0 && c < 3, 7 + wg);
  wg_fence();
  WgRS<64>::set<HI_SW32>(U, k.f[0], du);
  WgRS<64>::mma<HI_SW32>(U, k.f[1], du + 32);
  wg_commit();
  g_step(H, a, dg, dg + 64);
  wg_wait<1>();
  pin<32>(U);
  twiddle_fwd(e, U, k);
  wg_fence();
  g_step(U, e, dg, dg + 64);
  wg_wait<0>();
  pin<32>(U);
  pin<32>(H);
#pragma unroll
  for (int j = 0; j < 4; j++) H[4 * (j >> 1) + (j & 1)] += dv;
  float V[32];
#pragma unroll
  for (int p = 0; p < 2; p++) {
    products(a, H, U, p);
    wg_fence();
    WgRS<32>::set<HI_SW64>(V + 16 * p, a[2 * p], dg + 64);
    WgRS<32>::mma<HI_SW64>(V + 16 * p, a[2 * p + 1], dg);
    wg_commit();
  }
  const uint32_t za = cb + U_BYTES + (8 * w + (lane & 7)) * 128 + (((lane >> 3) ^ (lane & 7)) << 4);
  const uint32_t ya = cb + (lane >> 4) * 1024 + (8 * w + (lane & 7)) * 32 + ((((lane >> 3) ^ (lane >> 2)) & 1) << 4);
  wg_sync(1 + wg);
#pragma unroll
  for (int p = 0; p < 2; p++) {
    if (p == 0) wg_wait<1>();
    else wg_wait<0>();
    pin<16>(V + 16 * p);
#pragma unroll
    for (int i = 0; i < 4; i++) {
      const int j = i & 1;
      const float* x = V + 16 * p + 4 * j + (i & 2);
      e[p][i] = pack2(x[8], x[9]);
      e[2 + p][i] = pack2(x[0], x[1]);
      rot(e[p][i], e[2 + p][i], k.ta[1][j], k.tb[1][j]);
    }
    stsm4(za ^ (64 * p), e[p]);
    stsm4((za ^ (64 * p)) + 4096, e[2 + p]);
  }
  fence_async_smem();
  wg_sync(1 + wg);
  wg_fence();
  WgRS<64>::set<HI_SW128>(H, k.fi[0], dz);
#pragma unroll
  for (int ks = 1; ks < 4; ks++) WgRS<64>::mma<HI_SW128>(H, k.fi[ks], dz + 128 * ks);
  wg_commit();
  wg_wait<0>();
  pin<32>(H);
  if (lane == 0) mbar_arrive(bars + 8 * B_CVD);
  TSIF(w == 0, 88 + c);
#pragma unroll
  for (int j = 0; j < 8; j++)
    a[j >> 2][j & 3] = j < 2 ? pack2(H[4 * j], H[4 * j + 1]) : pack2(H[4 * j] + H[4 * j - 6], H[4 * j + 1] + H[4 * j - 5]);
  stsm4(ya, a[0]);
  stsm4(ya + 2048, a[1]);
  fence_async_smem();
  __syncwarp();
}

__device__ __forceinline__ void prep_slab(uint4* res, const uint2* sw, uint32_t sb, int slab, int w, int lane) {
  const int t = lane & 3, tp = (lane & 7) >> 1, pos = 8 * tp + 2 * (((lane >> 3) + tp) & 3) + (lane & 1);
  const uint32_t base = sb + OFF_KVS + slab * KVS_BYTES + pos * 128;
  uint32_t kk[2][4][4], vv[2][4];
  mbar_wait(sb + OFF_BAR + 8 * (B_KV + slab), 0);
#pragma unroll
  for (int h = 0; h < 2; h++) {
#pragma unroll
    for (int j = 0; j < 4; j++) {
      const uint32_t a = base + 128 * j;
      ldsm4t(kk[h][j], a + (((w + 4 * h) ^ ((a >> 7) & 7)) << 4));
    }
    const uint32_t a = base + KVS_V;
    ldsm4t(vv[h], a + (((w + 4 * h) ^ ((a >> 7) & 7)) << 4));
  }
#pragma unroll
  for (int h = 0; h < 2; h++) {
    uint32_t (&k)[4][4] = kk[h];
    uint32_t (&v)[4] = vv[h];
    const uint32_t w0 = __byte_perm(sw[h].x, 0, 0x1010), w1 = __byte_perm(sw[h].x, 0, 0x3232);
    const uint32_t w2 = __byte_perm(sw[h].y, 0, 0x1010), w3 = __byte_perm(sw[h].y, 0, 0x3232);
#pragma unroll
    for (int m = 0; m < 4; m++)
      v[m] = bmul(badd(badd(badd(bmul(k[0][m], w3), bmul(k[1][m], w2)), bmul(k[2][m], w1)), bmul(k[3][m], w0)), v[m]);
    uint32_t a[4];
#pragma unroll
    for (int m = 0; m < 4; m++) a[m] = (t & 1) ? v[(m + 3) & 3] : v[m];
    res[h] = (t & 2) ? make_uint4(a[2], a[3], a[0], a[1]) : make_uint4(a[0], a[1], a[2], a[3]);
  }
}

__device__ __forceinline__ void prep_gate(const Params& p, uint32_t sb, int b, int w, int lane) {
  uint2 gw[5], x[4][5];
#pragma unroll
  for (int j = 0; j < 5; j++) gw[j] = ldg64(reinterpret_cast<const uint2*>(p.gate_w) + lane + 32 * j);
#pragma unroll
  for (int i = 0; i < 4; i++)
#pragma unroll
    for (int j = 0; j < 5; j++)
      x[i][j] = ldg64(reinterpret_cast<const uint2*>(p.q) + (16 * b + 4 * w + i) * (DIM / 4) + lane + 32 * j);
  float s[4];
#pragma unroll
  for (int i = 0; i < 4; i++) {
    s[i] = 0.f;
#pragma unroll
    for (int j = 0; j < 5; j++) {
      const uint32_t m0 = bmul(x[i][j].x, gw[j].x), m1 = bmul(x[i][j].y, gw[j].y);
      s[i] += (bf_lo(m0) + bf_hi(m0)) + (bf_lo(m1) + bf_hi(m1));
    }
  }
  const bool h = lane & 16, q = lane & 8;
  const float a = (h ? s[2] : s[0]) + __shfl_xor_sync(0xffffffffu, h ? s[0] : s[2], 16);
  const float c = (h ? s[3] : s[1]) + __shfl_xor_sync(0xffffffffu, h ? s[1] : s[3], 16);
  float z = (q ? c : a) + __shfl_xor_sync(0xffffffffu, q ? a : c, 8);
#pragma unroll
  for (int o = 4; o > 0; o >>= 1) z += __shfl_xor_sync(0xffffffffu, z, o);
  z = bf_lo(pack2(z, 0.f));
  z = bf_lo(pack2(__fdividef(1.f, 1.f + __expf(-z)), 0.f));
  mbar_wait(sb + OFF_BAR + 8 * B_S3, 0);
  if ((lane & 7) == 0) asm volatile("st.shared.f32 [%0], %1;" ::"r"(sb + OFF_GATE + 64 * (b & 7) + 16 * w + (lane >> 1)), "f"(z) : "memory");
  fence_async_smem();
}

__device__ __forceinline__ uint32_t bmax(uint32_t a, uint32_t b) {
  uint32_t d;
  asm("max.bf16x2 %0, %1, %2;" : "=r"(d) : "r"(a), "r"(b));
  return d;
}
__device__ __forceinline__ void softmax_two(const float (&l)[2][2], uint32_t& p0, uint32_t& p1) {
  constexpr float kScale = 0.22360679774997896f, kLog2e = 1.4426950408889634f;
  const uint32_t r0 = pack2(l[0][0], l[1][0]), r1 = pack2(l[0][1], l[1][1]);
  const uint32_t x0 = pack2(bf_lo(r0) * kScale, bf_hi(r0) * kScale), x1 = pack2(bf_lo(r1) * kScale, bf_hi(r1) * kScale);
  uint32_t m = bmax(x0, x1);
  m = bmax(m, __shfl_xor_sync(0xffffffffu, m, 1));
  m = bmax(m, __shfl_xor_sync(0xffffffffu, m, 2));
  const float m0 = bf_lo(m) * kLog2e, m1 = bf_hi(m) * kLog2e;
  p0 = pack2(ex2(bf_lo(x0) * kLog2e - m0), ex2(bf_lo(x1) * kLog2e - m0));
  p1 = pack2(ex2(bf_hi(x0) * kLog2e - m1), ex2(bf_hi(x1) * kLog2e - m1));
}

__device__ __forceinline__ void halo_read(uint32_t (&kpv)[10], uint32_t (&vpv)[10], uint32_t (&tg)[7], const uint4* hp) {
#pragma unroll
  for (int j = 0; j < 7; j++) {
    uint32_t x0, x1, x2;
    asm volatile("ld.relaxed.gpu.global.v4.u32 {%0, %1, %2, %3}, [%4];"
                 : "=r"(x0), "=r"(x1), "=r"(x2), "=r"(tg[j]) : "l"(hp + 32 * j) : "memory");
    if (j < 4) kpv[3 * j] = x0; else vpv[3 * j - 10] = x0;
    if (j < 3) kpv[3 * j + 1] = x1; else vpv[3 * j - 9] = x1;
    if (j < 3) kpv[3 * j + 2] = x2; else if (j < 6) vpv[3 * j - 8] = x2;
  }
}

template <int ROT>
__device__ __forceinline__ void pack_qkv(const float* acc, uint32_t (&qlo)[10], uint32_t (&qhi)[10], uint32_t (&klo)[10],
                                         uint32_t (&khi)[10], uint32_t (&vlo)[10], uint32_t (&vhi)[10]) {
#pragma unroll
  for (int j = 0; j < 10; j++) {
    const int x = (j + ROT) % 10, tq = x < 8 ? x : 16 + x, tk = x < 8 ? 8 + x : 18 + x, tv = x < 8 ? 16 + x : 20 + x;
    khi[j] = pack2(acc[4 * tk + 2], acc[4 * tk + 3]);
    vhi[j] = movm(pack2(acc[4 * tv + 2], acc[4 * tv + 3]));
    qlo[j] = pack2(acc[4 * tq], acc[4 * tq + 1]);
    qhi[j] = pack2(acc[4 * tq + 2], acc[4 * tq + 3]);
    klo[j] = pack2(acc[4 * tk], acc[4 * tk + 1]);
    vlo[j] = pack2(acc[4 * tv], acc[4 * tv + 1]);
    asm volatile("" : "+r"(khi[j]), "+r"(qlo[j]), "+r"(qhi[j]), "+r"(klo[j]), "+r"(vlo[j]));
  }
}

template <int ROT> __device__ __forceinline__ void halo_send(const float* acc, uint4* ho, uint32_t tag) {
#pragma unroll
  for (int j = 0; j < 7; j++) {
    uint32_t x[3];
#pragma unroll
    for (int e = 0; e < 3; e++) {
      const int i = 3 * j + e, y = (i % 10 + ROT) % 10, tk = y < 8 ? 8 + y : 18 + y, tv = y < 8 ? 16 + y : 20 + y;
      x[e] = i < 10 ? pack2(acc[4 * tk + 2], acc[4 * tk + 3]) : i < 20 ? movm(pack2(acc[4 * tv + 2], acc[4 * tv + 3])) : 0u;
    }
    asm volatile("st.relaxed.gpu.global.v4.u32 [%0], {%1, %2, %3, %4};" ::"l"(ho + 32 * j), "r"(x[0]), "r"(x[1]), "r"(x[2]), "r"(tag) : "memory");
  }
}

__device__ __forceinline__ void attention(float* acc, uint32_t sb, int b, int par, int w, int lane, uint32_t tag) {
  const int g = lane >> 2, t = lane & 3;
  uint32_t klo[10], khi[10], vlo[10], vhi[10], qlo[10], qhi[10], kpv[10], vpv[10];
  if (w == 3 && b < NCTA - 8) {
    uint4* ho = g_halo + (b * 2 + par) * 224 + lane;
    if (tail_first(b & 7)) halo_send<8>(acc, ho, tag);
    else halo_send<0>(acc, ho, tag);
    TSIF(par == 0, 76);
    pin<120>(acc);
  }
  if (tail_first(b & 7)) pack_qkv<8>(acc, qlo, qhi, klo, khi, vlo, vhi);
  else pack_qkv<0>(acc, qlo, qhi, klo, khi, vlo, vhi);
  const uint32_t xa = sb + OFF_KVX + (par * 3) * 2560 + lane * 16;
  if (w < 3) {
    sts128(xa + w * 2560, khi[0], khi[1], khi[2], khi[3]);
    sts128(xa + w * 2560 + 512, khi[4], khi[5], khi[6], khi[7]);
    sts128(xa + w * 2560 + 1024, khi[8], khi[9], vhi[0], vhi[1]);
    sts128(xa + w * 2560 + 1536, vhi[2], vhi[3], vhi[4], vhi[5]);
    sts128(xa + w * 2560 + 2048, vhi[6], vhi[7], vhi[8], vhi[9]);
  }
  TSIF(par == 0 && w == 1, 64);
#pragma unroll
  for (int j = 0; j < 10; j++) vlo[j] = movm(vlo[j]);
  const bool far0 = 2 * t > g, far1 = 2 * t + 1 > g;
  const uint32_t mfar = (far0 ? 0x0000FFFFu : 0u) | (far1 ? 0xFFFF0000u : 0u);
  float slo[4][2], lg[2][2];
  uint32_t phi[4], plo[4], qml[4], qmh[4];
#pragma unroll
  for (int h = 0; h < 4; h++) {
    const int f = h == 0 ? 0 : h == 1 ? 3 : h == 2 ? 5 : 8, hf = h < 2 ? 2 : 7;
    const bool mine = (h & 1) ? t >= 2 : t < 2;
    qml[h] = mine ? qlo[hf] : 0u;
    qmh[h] = mine ? qhi[hf] : 0u;
    float a[4] = {0.f, 0.f, 0.f, 0.f}, c[4] = {0.f, 0.f, 0.f, 0.f};
    mma16816(a, qlo[f], qhi[f], qlo[f + 1], qhi[f + 1], klo[f], klo[f + 1]);
    mma16816(c, qlo[f], qhi[f], qlo[f + 1], qhi[f + 1], khi[f], khi[f + 1]);
    mma1688(a, qml[h], qmh[h], klo[hf]);
    mma1688(c, qml[h], qmh[h], khi[hf]);
    slo[h][0] = a[0];
    slo[h][1] = a[1];
    lg[h & 1][0] = far0 ? a[2] : c[2];
    lg[h & 1][1] = far1 ? a[3] : c[3];
    if (h & 1) softmax_two(lg, phi[h - 1], phi[h]);
  }
  TSIF(par == 0 && w == 1, 65);
  wg_sync(1 + par);
  TSIF(par == 0 && w == 1, 66);
  const bool nohist = (w == 0) && (b < 8);
  const uint4* hp = g_halo + ((b - 8) * 2 + par) * 224 + lane;
  uint32_t tg[7];
  if (w > 0) {
    const uint4 v0 = lds128(xa + (w - 1) * 2560), v1 = lds128(xa + (w - 1) * 2560 + 512), v2 = lds128(xa + (w - 1) * 2560 + 1024);
    const uint4 v3 = lds128(xa + (w - 1) * 2560 + 1536), v4 = lds128(xa + (w - 1) * 2560 + 2048);
    kpv[0] = v0.x; kpv[1] = v0.y; kpv[2] = v0.z; kpv[3] = v0.w; kpv[4] = v1.x; kpv[5] = v1.y; kpv[6] = v1.z; kpv[7] = v1.w;
    kpv[8] = v2.x; kpv[9] = v2.y; vpv[0] = v2.z; vpv[1] = v2.w; vpv[2] = v3.x; vpv[3] = v3.y; vpv[4] = v3.z; vpv[5] = v3.w;
    vpv[6] = v4.x; vpv[7] = v4.y; vpv[8] = v4.z; vpv[9] = v4.w;
  } else if (nohist) {
#pragma unroll
    for (int j = 0; j < 10; j++) kpv[j] = vpv[j] = 0u;
  } else {
    TSIF(par == 0, 77);
    halo_read(kpv, vpv, tg, hp);
  }
  if (w == 0 && !nohist) {
    int spins = 0;
    while (true) {
      bool ok = true;
#pragma unroll
      for (int j = 0; j < 7; j++) ok = ok && tg[j] == tag;
      if (__all_sync(0xffffffffu, ok) || ++spins > SPIN_LIMIT) break;
      halo_read(kpv, vpv, tg, hp);
    }
    TSIF(par == 0, 79);
  }
#pragma unroll
  for (int h = 0; h < 4; h++) {
    const int f = h == 0 ? 0 : h == 1 ? 3 : h == 2 ? 5 : 8, hf = h < 2 ? 2 : 7;
    float a[4] = {0.f, 0.f, 0.f, 0.f};
    mma16816(a, qlo[f], qhi[f], qlo[f + 1], qhi[f + 1], kpv[f], kpv[f + 1]);
    mma1688(a, qml[h], qmh[h], kpv[hf]);
    const float ninf = __int_as_float(0xff800000);
    lg[h & 1][0] = far0 ? (nohist ? ninf : a[0]) : slo[h][0];
    lg[h & 1][1] = far1 ? (nohist ? ninf : a[1]) : slo[h][1];
    if (h & 1) softmax_two(lg, plo[h - 1], plo[h]);
  }
  TSIF(par == 0 && w <= 1, 67 + w);
  uint32_t ov[20];
#pragma unroll
  for (int hp = 0; hp < 2; hp++) {
    const int hf = hp ? 7 : 2;
    float sh[4] = {0.f, 0.f, 0.f, 0.f}, i0 = 0.f, i1 = 0.f;
#pragma unroll
    for (int e = 0; e < 2; e++) {
      const int h = 2 * hp + e, f = h == 0 ? 0 : h == 1 ? 3 : h == 2 ? 5 : 8;
      const uint32_t a0 = plo[h] & mfar, a2 = plo[h] & ~mfar, a3 = phi[h] & mfar, c1 = phi[h] & ~mfar;
      float sum[4] = {0.f, 0.f, 0.f, 0.f};
      mma1688(sum, plo[h], phi[h], 0x3F803F80u);
      const float r0 = rcp(sum[0]), r1 = rcp(sum[2]);
#pragma unroll
      for (int j = f; j < f + 2; j++) {
        float o[4] = {0.f, 0.f, 0.f, 0.f};
        mma16816(o, a0, 0u, a2, a3, vpv[j], vlo[j]);
        mma1688(o, 0u, c1, vhi[j]);
        ov[2 * j] = pack2(o[0] * r0, o[1] * r0);
        ov[2 * j + 1] = pack2(o[2] * r1, o[3] * r1);
      }
      const bool mine = e ? g >= 4 : g < 4;
      mma16816(sh, a0, 0u, a2, a3, mine ? vpv[hf] : 0u, mine ? vlo[hf] : 0u);
      mma1688(sh, 0u, c1, mine ? vhi[hf] : 0u);
      if (e == 0 || t >= 2) {
        i0 = r0;
        i1 = r1;
      }
    }
    ov[2 * hf] = pack2(sh[0] * i0, sh[1] * i0);
    ov[2 * hf + 1] = pack2(sh[2] * i1, sh[3] * i1);
  }
  TS(32 + 4 * par + w);
  mbar_wait(sb + OFF_BAR + 8 * B_P1, 0);
  const uint32_t oa = sb + OFF_OA + (lane >> 4) * 2048 + (32 * w + 2 * (lane & 15) + par) * 16;
#pragma unroll
  for (int j = 0; j < 5; j++) stsm4(oa + 4096 * j, ov + 4 * j);
  TSIF(par == 0 && w == 0, 120);
  fence_async_smem();
  TSIF(par == 0 && w == 0, 121);
  __syncwarp();
  if (lane == 0) mbar_arrive(sb + OFF_BAR + 8 * B_ATTN);
  TSM(w == 0 || w == 2, 122 + par + (w == 2 ? 3 : 0));
}

struct Maps {
  CUtensorMap x, wm, wt, k, v, y, wo, qm, qt, om, ot, yl, ol;
};

__device__ __forceinline__ void load_stage(uint32_t sb, int kb, int b, const Maps& m) {
  const uint32_t st = sb + (kb & 3) * STAGE_BYTES, bar = sb + OFF_BAR + 8 * (B_FULL1 + (kb & 3));
  const int r = b >> 3, hg = b & 7, slab = kb - KV_KB;
  const bool kv = slab >= 0 && slab < 5;
  const uint32_t kbar = sb + OFF_BAR + 8 * (B_KV + slab), dst = sb + OFF_KVS + slab * KVS_BYTES;
  mbar_expect_tx(bar, STAGE_BYTES);
  if (kv) mbar_expect_tx(kbar, KVS_BYTES);
  tma_3d(st, &m.x, 64 * kb, 64 * r, 0, bar);
  tma_3d(st + ST_W, &m.wm, 80 * hg + (tail_first(hg) ? 16 : 0), 64 * kb, 0, bar);
  tma_3d(st + ST_WT, &m.wt, 80 * hg + (tail_first(hg) ? 0 : 64), 64 * kb, 0, bar);
  if (kv) tma_3d(dst, &m.k, 0, 32 * (b >> 1) - 3, 2 * slab + (b & 1), kbar);
  if (kv) tma_3d(dst + KVS_V, &m.v, 0, 32 * (b >> 1), 2 * slab + (b & 1), kbar);
}

__global__ void __launch_bounds__(NTHR, 1) fused_kernel(const __grid_constant__ Maps m, const Params p) {
  extern __shared__ __align__(1024) uint8_t smem[];
  const uint32_t sb = (uint32_t)__cvta_generic_to_shared(smem);
  const uint32_t bars = sb + OFF_BAR;
  const int tid = threadIdx.x, lane = tid & 31;
  int b = blockIdx.x;
  b = (((b & 63) >> 3) * 2 + (b & 1)) * 8 + (((b < 64 ? 0x6521 : 0x7430) >> (4 * ((b >> 1) & 3))) & 7);
  const int r = b >> 3, hg = b & 7;

  if (tid == T_ISSUE) {
    TSM(true, 0);
    mbar_init(bars + 8 * B_F0, 1);
    fence_async_smem();
    mbar_expect_tx(bars + 8 * B_F0, ST_WT);
    tma_3d(sb, &m.x, 0, 64 * r, 0, bars + 8 * B_F0);
    tma_3d(sb + ST_W, &m.wm, 80 * hg + (tail_first(hg) ? 16 : 0), 0, 0, bars + 8 * B_F0);
#pragma unroll
    for (int i = 0; i < 4; i++) mbar_init(bars + 8 * (B_FULL1 + i), 1);
    fence_async_smem();
    mbar_expect_tx(bars + 8 * B_FULL1, STAGE_BYTES - ST_WT);
    tma_3d(sb + ST_WT, &m.wt, 80 * hg + (tail_first(hg) ? 0 : 64), 0, 0, bars + 8 * B_FULL1);
    load_stage(sb, 1, b, m);
  } else if (tid == T_INIT) {
#pragma unroll
    for (int i = 0; i < B_F0; i++) mbar_init(bars + 8 * i, i < B_GATE ? 8 : i < B_CVD ? 4 : i == B_CVD ? 20 : 1);
    fence_async_smem();
  }
  const int warp = __shfl_sync(0xffffffffu, tid >> 5, 0), wg = warp >> 2, w = warp & 3;
  __syncthreads();

  if (wg == 3) {
    asm volatile("setmaxnreg.dec.sync.aligned.u32 56;");
    if (w == 0) {
      if (lane == 0) {
#pragma unroll 1
        for (int kb = 2; kb < 10; kb++) {
          if (kb >= 4) mbar_wait(bars + 8 * (kb == 7 ? B_E3 : B_EMPTY1 + (kb & 3)), (kb >> 3) & 1);
          TSIF(kb >= 4, 44 + kb);
          load_stage(sb, kb, b, m);
          TSIF(kb == 3, 60);
          if (kb == TRIG_KB) mbar_arrive(bars + 8 * B_LAST);
        }
        mbar_wait(bars + 8 * B_WOP, 0);
        mbar_wait(bars + 8 * WL_TRIG, 0);
        mbar_wait(bars + 8 * B_EPOCH, 0);
        flag_wait(g_cnt + C_W + 32 * hg, (lds32(sb + OFF_EPOCH) + 1) * 16);
        TS(30);
#pragma unroll 1
        for (int j = 0; j < 8; j++) {
          if (j >= 6) mbar_wait(bars + 8 * (B_EMPTY2 + j - 6), 0);
          if (j == 4) mbar_wait(bars + 8 * (RB32 & 2 ? B_ORB : B_ATTN), 0);
          TSIF(j >= 6, 100 + j);
          mbar_expect_tx(bars + 8 * (B_FULL2 + j), j == 0 ? WO_BYTES : j == 5 ? O_BYTES + WO_BYTES + 512 : O_BYTES + WO_BYTES);
          bulk_load(sb + off_w(j), g_WO + (hg * 8 + step_src(hg, j)) * 800, WO_BYTES, bars + 8 * (B_FULL2 + j));
        }
        mbar_wait(bars + 8 * (Q_SWAP ? B_YSIG : B_EMPTY2 + Q_SLOT), 0);
        if (Q_SWAP == 2) mbar_wait(bars + 8 * (B_FULL2 + 6), 0);
        mbar_expect_tx(bars + 8 * B_QF, O_BYTES);
        tma_2d(sb + OFF_QS, &m.qm, 80 * hg, 128 * r, bars + 8 * B_QF);
        tma_2d(sb + OFF_QT, &m.qt, 80 * hg + 64, 128 * r, bars + 8 * B_QF);
      }
    } else if (w == 1) {
      unsigned epoch = 0;
      if (lane == 0) {
        epoch = atomicAdd(g_cnt + C_LAUNCH, 1u) / NCTA;
        asm volatile("st.shared.u32 [%0], %1;" ::"r"(sb + OFF_EPOCH), "r"(epoch) : "memory");
        mbar_arrive(bars + 8 * B_EPOCH);
        mbar_wait(bars + 8 * B_KVD, 0);
        mbar_expect_tx(bars + 8 * B_HB, 5 * 4096);
#pragma unroll 1
        for (int c = 0; c < 5; c++) {
          if (c == 3) mbar_wait(bars + 8 * B_S3, 0);
          bulk_load(sb + off_ch(c) + U_BYTES, p.ssm_k + (5 * b + c) * SEQ, 4096, bars + 8 * B_HB);
        }
#pragma unroll
        for (int c = 0; c < 4; c++) mbar_expect_tx(bars + 8 * (B_U + c), c < 3 ? U_BYTES : 2 * U_BYTES);
        const uint4* usrc = g_U + 5 * b * U_PITCH;
        mbar_wait(bars + 8 * B_USIG, 0);
        flag_wait(g_cnt + C_PREP + 32 * (b & 15), (epoch + 1) * NCTA);
        TS(23);
#pragma unroll
        for (int c = 0; c < 5; c++) {
          if (c == 3) mbar_wait(bars + 8 * (B_U + 2), 0);
          bulk_load(sb + off_ch(c), usrc + c * U_PITCH, U_BYTES, bars + 8 * (B_U + (c < 3 ? c : 3)));
          TSIF(c == 0 || c == 4, 116 + (c >> 2));
        }
      }
      epoch = __shfl_sync(0xffffffffu, epoch, 0);
      if (lane < 8) {
        const int src = (b & ~7) | step_src(hg, lane);
        mbar_wait(bars + 8 * B_ATTN, 0);
        TS(20);
        bool seen = false;
#pragma unroll 1
        for (int spins = 0; spins < SPIN_LIMIT; spins++) {
          const bool now = !seen && (int)(flag_read(g_cnt + C_O + 32 * src) - (epoch + 1)) >= 0;
          if (now && lane >= 1 && lane < 4) bulk_load(sb + off_o(lane), g_O + src * 1280, O_BYTES, bars + 8 * (B_FULL2 + lane));
          seen = seen || now;
          if (__all_sync(0xff, seen)) break;
        }
        TS(21);
        if (lane == 5) bulk_load(sb + OFF_GATE, g_gate + 128 * r, 512, bars + 8 * (B_FULL2 + 5));
#pragma unroll 1
        for (int j = 4; j < 8; j++) {
          if (lane == j) {
            mbar_wait(bars + 8 * (j < 6 ? B_C34 : B_EMPTY2 + j - 6), 0);
            bulk_load(sb + off_o(j), g_O + src * 1280, O_BYTES, bars + 8 * (B_FULL2 + j));
          }
          __syncwarp(0xff);
        }
        TS(22);
      }
    } else if (w == 2) {
      mbar_wait(bars + 8 * B_PREP, 0);
      flag_signal(g_cnt + C_PREP, 16, lane);
      TS(25);
      if (lane == 0) {
        mbar_arrive(bars + 8 * B_USIG);
        mbar_expect_tx(bars + 8 * B_ORB, (RB32 & 2 ? O_BYTES / 4 : O_BYTES) + 64);
        mbar_wait(bars + 8 * B_GATE, 0);
        publish(g_gate + 16 * b, sb + OFF_GATE + 64 * hg, 64, bars + 8 * B_ORB);
        mbar_wait(bars + 8 * B_ATTN, 0);
        if (RB32 & 2) {
          bulk_store(g_O + b * 1280, sb + OFF_OA, O_BYTES);
          bulk_wait_read();
          tma_2d(sb + OFF_KVX + 10240, &m.ol, 48, b * 160, bars + 8 * B_ORB);
        } else {
          publish(g_O + b * 1280, sb + OFF_OA, O_BYTES, bars + 8 * B_ORB);
        }
        TS(74);
        mbar_wait(bars + 8 * B_ORB, 0);
        flag_bump(g_cnt + C_O + 32 * b);
        TS(26);
        mbar_arrive(bars + 8 * B_OSIG);
      }
    } else {
      if (lane == 0) {
        uint4* dst = g_WO + (hg * 8 + (r >> 1)) * 800 + (r & 1) * 80;
        mbar_wait(bars + 8 * B_S3, 0);
        asm volatile("cp.async.bulk.prefetch.L2.global [%0], 6400;" ::"l"(p.wo + b * 3200) : "memory");
        mbar_wait(bars + 8 * B_P1, 0);
        mbar_wait(bars + 8 * WB_TRIG, 0);
        mbar_expect_tx(bars + 8 * B_WST, WO_BYTES / 2);
        tma_3d(sb + OFF_WA, &m.wo, 0, 40 * r, 5 * hg, bars + 8 * B_WST);
        mbar_wait(bars + 8 * B_WST, 0);
#pragma unroll 1
        for (int n = 0; n < 5; n++) bulk_store(dst + 160 * n, sb + OFF_WA + 1280 * n, 1280);
        bulk_wait_read();
        mbar_expect_tx(bars + 8 * B_WST, WO_BYTES / 2);
#pragma unroll 1
        for (int n = 0; n < 5; n++) bulk_load(sb + OFF_WA + 1280 * n, dst + 160 * n, 1280, bars + 8 * B_WST);
        mbar_wait(bars + 8 * B_WST, 1);
        flag_bump(g_cnt + C_W + 32 * hg);
        mbar_arrive(bars + 8 * B_WOP);
        TS(71);
        mbar_expect_tx(bars + 8 * B_C34, 3 * (RB32 & 1 ? 1024 : U_BYTES));
        mbar_expect_tx(bars + 8 * B_YRB, 2 * (RB32 & 1 ? 1024 : U_BYTES));
#pragma unroll 1
        for (int c = 0; c < 5; c++) {
          mbar_wait(bars + 8 * (B_YST + c), 0);
          if (RB32 & 1) {
            bulk_store(g_U + (5 * b + c) * U_PITCH, sb + off_ch(c), U_BYTES);
            bulk_wait_read();
            tma_2d(sb + off_ch(c), &m.yl, 48, (5 * b + c) * (U_PITCH / 8), bars + 8 * (c < 3 ? B_C34 : B_YRB));
          } else {
            publish(g_U + (5 * b + c) * U_PITCH, sb + off_ch(c), U_BYTES, bars + 8 * (c < 3 ? B_C34 : B_YRB));
          }
        }
        TS(75);
        mbar_wait(bars + 8 * B_C34, 0);
        mbar_wait(bars + 8 * B_YRB, 0);
        flag_bump(g_cnt + C_Y + 32 * (b >> 4));
        TS(27);
        mbar_arrive(bars + 8 * B_YSIG);
        mbar_expect_tx(bars + 8 * B_YFULL, 20480);
        flag_wait(g_cnt + C_Y + 32 * hg, (lds32(sb + OFF_EPOCH) + 1) * 16);
        TS(24);
        if (Q_SWAP) mbar_wait(bars + 8 * (B_EMPTY2 + 2), 0);
        tma_2d(sb + OFF_YT, &m.y, 128 * r, 80 * hg, bars + 8 * B_YFULL);
        tma_2d(sb + OFF_YT + 10240, &m.y, 128 * r + 64, 80 * hg, bars + 8 * B_YFULL);
      }
    }
  } else {
    asm volatile("setmaxnreg.inc.sync.aligned.u32 152;");
    if (wg < 2) {
      float acc[120];
#pragma unroll
      for (int i = 0; i < 120; i++) acc[i] = 0.f;
      const uint32_t da = desc_lo(sb + wg * 8192, 16), db = desc_lo(sb + ST_W, 8192), dc = desc_lo(sb + ST_WT, 2048);
      mbar_wait(bars + 8 * B_F0, 0);
      TSIF(w == 0 && wg == 0, 1);
      wg_fence();
#pragma unroll
      for (int k = 0; k < 4; k++) WgSST<192>::mma<HI_SW128, HI_SW128>(acc, da + 2 * k, db + 128 * k, 1);
      wg_commit();
      mbar_wait(bars + 8 * B_FULL1, 0);
      wg_fence();
#pragma unroll
      for (int k = 0; k < 4; k++) WgSST<48>::mma<HI_SW128, HI_SW32>(acc + 96, da + 2 * k, dc + 32 * k, 1);
      wg_commit();
#pragma unroll 1
      for (int kb = 1; kb < 10; kb++) {
        mbar_wait(bars + 8 * (B_FULL1 + (kb & 3)), (kb >> 2) & 1);
        const uint32_t so = (kb & 3) * (STAGE_BYTES >> 4);
        wg_fence();
#pragma unroll
        for (int k = 0; k < 4; k++) {
          WgSST<192>::mma<HI_SW128, HI_SW128>(acc, da + so + 2 * k, db + so + 128 * k, 1);
          WgSST<48>::mma<HI_SW128, HI_SW32>(acc + 96, da + so + 2 * k, dc + so + 32 * k, 1);
        }
        wg_commit();
        wg_wait<1>();
        if (lane == 0) mbar_arrive(bars + 8 * (kb == 4 ? B_E3 : B_EMPTY1 + ((kb - 1) & 3)));
      }
      mbar_wait(bars + 8 * B_EPOCH, 0);
      const uint32_t tag = lds32(sb + OFF_EPOCH) + 1;
      mbar_wait(bars + 8 * B_S3, 0);
      wg_wait<0>();
      pin<120>(acc);
      if (lane == 0) mbar_arrive(bars + 8 * B_P1);
      TSM(w == 0, 3 + wg);
      attention(acc, sb, b, wg, w, lane, tag);
    } else {
      const int tw = tid & 127, chl = 64 * (b & 1) + 8 * w + (lane >> 2);
      uint4* up = g_U + chl * U_PITCH + ((4 * (b >> 1) + (lane & 3)) ^ ((b >> 2) & 1));
      uint2 sw[10];
      uint32_t dv = 0;
      if (lane < 5) dv = __ldg(reinterpret_cast<const unsigned short*>(p.ssm_D) + 5 * b + lane);
#pragma unroll
      for (int i = 0; i < 10; i++) sw[i] = ldg64(reinterpret_cast<const uint2*>(p.shift_k) + chl + 128 * (i >> 1) + 32 * (i & 1));
      uint32_t tab[12];
      uint32_t tt[2];
      fft_tables(tab, tw);
      fft_twiddles(tt, tw);
      uint4 res[10];
#pragma unroll
      for (int i = 0; i < 10; i++) res[i] = make_uint4(0, 0, 0, 0);
#pragma unroll 1
      for (int slab = 0; slab < 5; slab++) {
#pragma unroll
        for (int i = 0; i < 8; i++) res[i] = res[i + 2];
        prep_slab(res + 8, sw, sb, slab, w, lane);
        TSIF(w == 0, 99 + 4 * slab);
#pragma unroll
        for (int i = 0; i < 8; i++) sw[i] = sw[i + 2];
      }
      TSIF(w == 0, 28);
      __syncwarp();
      if (lane == 0) mbar_arrive(bars + 8 * B_KVD + ((res[8].x ^ res[9].x) & p.zero));
      mbar_wait(bars + 8 * B_KVD, 0);
      fft_tables_store(tab, sb, tw);
      mbar_wait(bars + 8 * B_LAST, 0);
#pragma unroll
      for (int i = 0; i < 10; i++) up[(128 * (i >> 1) + 32 * (i & 1)) * U_PITCH] = res[i];
      __syncwarp();
      if (lane == 0) mbar_arrive(bars + 8 * B_PREP);
      TSIF(w == 0, 5);
      mbar_wait(bars + 8 * B_LAST, 0);
      prep_gate(p, sb, b, w, lane);
      __syncwarp();
      if (lane == 0) mbar_arrive(bars + 8 * B_GATE);
      TSIF(w == 0, 72);
      mbar_wait(bars + 8 * B_HB, 0);
      TSIF(w == 0, 2);
      const uint32_t ha = sb + U_BYTES + ((tw >> 3) * 16 + 8 + (tw & 7)) * 16;
      uint4 hv[5];
#pragma unroll
      for (int c = 0; c < 5; c++) hv[c] = lds128(ha + off_ch(c));
      __syncwarp();
#pragma unroll
      for (int c = 0; c < 5; c++) sts128((ha ^ 16) + off_ch(c), hv[c].x, hv[c].y, hv[c].z, hv[c].w);
      asm volatile("st.shared.v2.u32 [%0], {%1, %2};" ::"r"(sb + OFF_TT + 8 * tw), "r"(tt[0]), "r"(tt[1]) : "memory");
      if (tw < 5) asm volatile("st.shared.f32 [%0], %1;" ::"r"(sb + OFF_D + 4 * tw), "f"(bf_lo(dv) * 0.125f) : "memory");
      fence_async_smem();
      __syncwarp();
      if (lane == 0) mbar_arrive(bars + 8 * B_HA);
      TSIF(w == 0, 6);
    }

    FftConst fc;
    TSM(w == 0 && wg == 0, 104);
    mbar_wait(bars + 8 * B_HA, 0);
    fft_matrices(fc, sb, w, lane);
    TSM(w == 0 && wg == 0, 105);
    TSM(w == 0 && wg == 2, 124);
#pragma unroll 1
    for (uint32_t tasks = wg == 0 ? TASK0 : wg == 1 ? TASK1 : TASK2; tasks; tasks >>= 4) {
      const int c = (tasks & 7) - 1;
      conv_channel(fc, sb, c, wg, w, lane);
      if (lane == 0) mbar_arrive(bars + 8 * (B_YST + c));
      TSM(w == 0, 10 + c);
    }

    if (wg < 2) {
      const int g = lane >> 2;
      float acc[40];
#pragma unroll
      for (int i = 0; i < 40; i++) acc[i] = 0.f;
      const uint32_t da = desc_lo(sb + wg * 1024, 2048), db = desc_lo(sb, 2560);
      mbar_wait(bars + 8 * B_ORB, 0);
      mbar_wait(bars + 8 * B_FULL2, 0);
      mbar_wait(bars + 8 * B_CVD, 0);
      TSM(w == 0, 15 + wg);
#pragma unroll 1
      for (int j = 0; j < 8; j++) {
        mbar_wait(bars + 8 * (B_FULL2 + j), 0);
        TSM(w == 0 && wg == 0, 44 + (j < 4 ? j : j + 6));
        const uint32_t oa = da + (off_o(j) >> 4), ob = db + (off_w(j) >> 4);
        wg_fence();
#pragma unroll
        for (int k = 0; k < 5; k++) WgSST<80>::mma<HI_NONE, HI_SW32>(acc, oa + 256 * k, ob + 32 * k, 1);
        wg_commit();
        wg_wait<1>();
        if (j >= 1 && j <= 4 && lane == 0) mbar_arrive(bars + 8 * (B_EMPTY2 + j - 1));
      }
      TSIF(w == 0 && wg == 0, 113);
      const int tr = 64 * wg + 16 * w + (lane & 15);
      const uint32_t fm = sb + OFF_QS + tr * 128, fx = (lane >> 4) ^ (tr & 7);
      const uint32_t ft = sb + OFF_QT + tr * 32 + (((lane >> 4) ^ (tr >> 2)) & 1) * 16;
      const float g0 = __uint_as_float(lds32(sb + OFF_GATE + (64 * wg + 16 * w + g) * 4));
      const float g1 = __uint_as_float(lds32(sb + OFF_GATE + (64 * wg + 16 * w + 8 + g) * 4));
      const uint32_t ga = pack2(g0, g0), gb = pack2(g1, g1);
      const uint32_t na = pack2(1.f - g0, 1.f - g0), nb = pack2(1.f - g1, 1.f - g1);

      uint32_t qf[20];
      mbar_wait(bars + 8 * B_QF, 0);
      TSM(w == 0 && wg == 0, 99);
#pragma unroll
      for (int j = 0; j < 5; j++) ldsm4(qf + 4 * j, j < 4 ? fm + ((fx ^ (2 * j)) << 4) : ft);
#pragma unroll
      for (int i = 0; i < 20; i++) {
        qf[i] = bmul((i & 1) ? gb : ga, qf[i]);
        asm volatile("" : "+r"(qf[i]));
      }

      wg_wait<0>();
      pin<40>(acc);
      TSM(w == 0, 17 + wg);
      uint32_t pb[20];
#pragma unroll
      for (int j = 0; j < 10; j++) {
        pb[2 * j] = bmul(na, pack2(acc[4 * j], acc[4 * j + 1]));
        pb[2 * j + 1] = bmul(nb, pack2(acc[4 * j + 2], acc[4 * j + 3]));
        asm volatile("" : "+r"(pb[2 * j]), "+r"(pb[2 * j + 1]));
      }
      const uint32_t ya = sb + OFF_YT + wg * 10240 + ((lane >> 4) * 8 + (lane & 7)) * 128 +
                          (((2 * w + (((lane >> 3) & 1) ^ wg)) ^ (lane & 7)) << 4);
      mbar_wait(bars + 8 * B_YFULL, 0);
      TSM(w == 0 && wg == 0, 19);
#pragma unroll
      for (int j = 0; j < 5; j++) {
        uint32_t y[4];
        ldsm4t(y, ya + 2048 * j);
#pragma unroll
        for (int i = 0; i < 4; i++)
          qf[4 * j + i] = bfma(qf[4 * j + i], y[i], pb[4 * j + i]);
      }
#pragma unroll
      for (int j = 0; j < 5; j++) stsm4(j < 4 ? fm + ((fx ^ (2 * j)) << 4) : ft, qf + 4 * j);
      fence_async_smem();
      __syncwarp();
      if (lane == 0) {
        const int row = 64 * wg + 16 * w;
        asm volatile("cp.async.bulk.tensor.2d.global.shared::cta.bulk_group [%0, {%2, %3}], [%1];"
                     ::"l"(&m.om), "r"(sb + OFF_QS + row * 128), "r"(80 * hg), "r"(128 * r + row) : "memory");
        asm volatile("cp.async.bulk.tensor.2d.global.shared::cta.bulk_group [%0, {%2, %3}], [%1];"
                     ::"l"(&m.ot), "r"(sb + OFF_QT + row * 32), "r"(80 * hg + 64), "r"(128 * r + row) : "memory");
        asm volatile("cp.async.bulk.commit_group;\ncp.async.bulk.wait_group.read 0;" ::: "memory");
      }
      TSM(w == 0 || w == 3, 40 + 2 * wg + (w & 1));
    }
  }
}

typedef CUresult (*EncodeFn)(CUtensorMap*, CUtensorMapDataType, cuuint32_t, void*, const cuuint64_t*, const cuuint64_t*,
                             const cuuint32_t*, const cuuint32_t*, CUtensorMapInterleave, CUtensorMapSwizzle,
                             CUtensorMapL2promotion, CUtensorMapFloatOOBfill);

void encode(EncodeFn fn, CUtensorMap* tm, const void* base, int rank, const cuuint64_t* dims, const cuuint64_t* strides,
            const cuuint32_t* box, CUtensorMapSwizzle swz) {
  const cuuint32_t ones[3] = {1, 1, 1};
  fn(tm, CU_TENSOR_MAP_DATA_TYPE_BFLOAT16, rank, const_cast<void*>(base), dims, strides, box, ones,
     CU_TENSOR_MAP_INTERLEAVE_NONE, swz, CU_TENSOR_MAP_L2_PROMOTION_L2_128B, CU_TENSOR_MAP_FLOAT_OOB_FILL_NONE);
}

}

extern "C" void kernel_launch(void* const* d_in, const int* in_sizes, int n_in, void* d_out, int out_size) {
  (void)in_sizes; (void)n_in; (void)out_size;
  Params p;
  p.q = (const __nv_bfloat16*)d_in[0];
  p.k = (const __nv_bfloat16*)d_in[1];
  p.v = (const __nv_bfloat16*)d_in[2];
  p.shift_k = (const __nv_bfloat16*)d_in[3];
  p.ssm_k = (const __nv_bfloat16*)d_in[4];
  p.ssm_D = (const __nv_bfloat16*)d_in[5];
  p.wqkv = (const __nv_bfloat16*)d_in[7];
  p.wo = (const __nv_bfloat16*)d_in[8];
  p.gate_w = (const __nv_bfloat16*)d_in[9];
  p.out = (__nv_bfloat16*)d_out;
  p.zero = 0;

  static EncodeFn fn = nullptr;
  static void *yaddr = nullptr, *oaddr = nullptr;
  if (!fn) {
    cudaDriverEntryPointQueryResult qr;
    void* f = nullptr;
    cudaGetDriverEntryPoint("cuTensorMapEncodeTiled", &f, cudaEnableDefault, &qr);
    fn = (EncodeFn)f;
    cudaGetSymbolAddress(&yaddr, g_U);
    cudaGetSymbolAddress(&oaddr, g_O);
    cudaFuncSetAttribute(fused_kernel, cudaFuncAttributeMaxDynamicSharedMemorySize, SMEM_BYTES);
  }
  Maps m;
  {
    const cuuint64_t dims[3] = {640, 1024, 2}, st[2] = {2560, 1280};
    const cuuint32_t box[3] = {64, 64, 2};
    encode(fn, &m.x, p.q, 3, dims, st, box, CU_TENSOR_MAP_SWIZZLE_128B);
  }
  {
    const cuuint64_t dims[3] = {640, 640, 3}, st[2] = {3840, 1280};
    const cuuint32_t box[3] = {64, 64, 3}, boxt[3] = {16, 64, 3};
    encode(fn, &m.wm, p.wqkv, 3, dims, st, box, CU_TENSOR_MAP_SWIZZLE_128B);
    encode(fn, &m.wt, p.wqkv, 3, dims, st, boxt, CU_TENSOR_MAP_SWIZZLE_32B);
  }
  {
    const cuuint64_t dims[3] = {64, 2048, 10}, st[2] = {1280, 128};
    const cuuint32_t boxk[3] = {64, 35, 1}, boxv[3] = {64, 32, 1};
    encode(fn, &m.k, p.k, 3, dims, st, boxk, CU_TENSOR_MAP_SWIZZLE_128B);
    encode(fn, &m.v, p.v, 3, dims, st, boxv, CU_TENSOR_MAP_SWIZZLE_128B);
  }
  {
    const cuuint64_t dims[3] = {16, 640, 40}, st[2] = {1280, 32};
    const cuuint32_t box[3] = {16, 40, 5};
    encode(fn, &m.wo, p.wo, 3, dims, st, box, CU_TENSOR_MAP_SWIZZLE_32B);
  }
  {
    const cuuint64_t dims[2] = {2048, 640}, st[1] = {U_PITCH * 16};
    const cuuint32_t box[2] = {64, 80};
    encode(fn, &m.y, yaddr, 2, dims, st, box, CU_TENSOR_MAP_SWIZZLE_128B);
    const cuuint64_t dl[2] = {64, DIM * U_PITCH / 8}, dol[2] = {64, NCTA * 160}, sl[1] = {128};
    const cuuint32_t bl[2] = {16, 32}, bol[2] = {16, 160};
    encode(fn, &m.yl, yaddr, 2, dl, sl, bl, CU_TENSOR_MAP_SWIZZLE_NONE);
    encode(fn, &m.ol, oaddr, 2, dol, sl, bol, CU_TENSOR_MAP_SWIZZLE_NONE);
  }
  {
    const cuuint64_t dims[2] = {640, 2048}, st[1] = {1280};
    const cuuint32_t bqm[2] = {64, 128}, bqt[2] = {16, 128}, bom[2] = {64, 16}, bot[2] = {16, 16};
    encode(fn, &m.qm, p.q, 2, dims, st, bqm, CU_TENSOR_MAP_SWIZZLE_128B);
    encode(fn, &m.qt, p.q, 2, dims, st, bqt, CU_TENSOR_MAP_SWIZZLE_32B);
    encode(fn, &m.om, p.out, 2, dims, st, bom, CU_TENSOR_MAP_SWIZZLE_128B);
    encode(fn, &m.ot, p.out, 2, dims, st, bot, CU_TENSOR_MAP_SWIZZLE_32B);
  }
  fused_kernel<<<NCTA, NTHR, SMEM_BYTES>>>(m, p);
}
```

```cpp
#include <cuda.h>
#include <cuda_bf16.h>
#include <cuda_runtime.h>
#include <stdint.h>

namespace {

constexpr int SEQ = 2048, DIM = 640, NCTA = 128, NTHR = 512;

#define TRIG_KB 9
#define KV_KB 2
#define DEV_EXIT 0
#define FENCE_LO 0
#define FENCE_HI 0
#define WB_TRIG B_USIG
#define T_ISSUE 256
#define RB32 3
#define Q_TRIG (B_U + 3)
#define T_INIT 448
#define TASK0 0x3
#define TASK1 0x52
#define TASK2 0x41
#define WL_TRIG B_WOP

constexpr uint32_t STAGE_BYTES = 47104, ST_W = 16384, ST_WT = 40960;
constexpr uint32_t OFF_KVS = 188416, KVS_V = 4480, KVS_BYTES = 8576;
constexpr uint32_t O_BYTES = 20480, WO_BYTES = 12800;
constexpr uint32_t OFF_OA = 0;
constexpr uint32_t OFF_YT = 2 * O_BYTES;
constexpr uint32_t OFF_WC = 81920;
constexpr uint32_t OFF_WA = 94720;
constexpr uint32_t OFF_GATE = 145920;
constexpr uint32_t OFF_TT = 146432;
constexpr uint32_t OFF_KVX = 148480;
constexpr uint32_t CH_BYTES = 8192, U_BYTES = 4096;
constexpr uint32_t OFF_CH3 = 163840;
constexpr uint32_t OFF_QS = 180224, OFF_QT = 221184;
constexpr uint32_t OFF_CH0 = 196608;
constexpr uint32_t OFF_FT = 225280, OFF_GT = 229376;
constexpr uint32_t OFF_BAR = 231936;
constexpr uint32_t SMEM_BYTES = OFF_BAR + 512;

enum : uint32_t {
  B_EMPTY1 = 0, B_S3 = 3, B_E3 = 4, B_EMPTY2 = 5, B_ATTN = 9, B_P1 = 10,
  B_GATE = 11, B_HA = 12, B_KVD = 13, B_PREP = 14, B_YST = 15,
  B_CVD = 20,
  B_FULL2 = 21, B_U = 29, B_KV = 33, B_HB = 38, B_C34 = 39, B_YRB = 40, B_YFULL = 41, B_EPOCH = 42, B_LAST = 43, B_OSIG = 44,
  B_WOP = 45, B_USIG = 46, B_WST = 47, B_QF = 48, B_ORB = 49, B_YSIG = 50,
  B_F0 = 51, B_FULL1 = 52
};
constexpr uint32_t OFF_EPOCH = OFF_BAR + 8 * 58, OFF_D = OFF_BAR + 8 * 60;
__device__ __forceinline__ uint32_t off_o(int j) { return j < 4 ? OFF_OA + j * O_BYTES : j == 4 ? OFF_CH0 : j == 5 ? OFF_CH3 : OFF_OA + (j - 6) * O_BYTES; }
__device__ __forceinline__ uint32_t off_w(int j) { return j < 4 ? OFF_WA + j * WO_BYTES : j == 4 ? OFF_KVX : j == 5 ? OFF_WC : OFF_WA + (j - 6) * WO_BYTES; }
__device__ __forceinline__ int step_src(int hg, int j) { return j == 0 ? hg : j <= hg ? j - 1 : j; }
__device__ __forceinline__ bool tail_first(int hg) { return (hg & 3) == 3; }
__device__ __forceinline__ uint32_t off_ch(int c) { return (c < 3 ? OFF_CH0 : OFF_CH3 - 3 * CH_BYTES) + c * CH_BYTES; }

#define U_PITCH 264
__device__ __align__(1024) uint4 g_U[DIM * U_PITCH];
__device__ __align__(128) uint4 g_O[NCTA * 1280];
__device__ uint4 g_WO[64 * 800];
__device__ uint4 g_halo[NCTA * 2 * 7 * 32];
__device__ __align__(128) float g_gate[SEQ];
__device__ unsigned g_cnt[32 * (1 + 2 * 16 + 8 + NCTA)];
constexpr int C_LAUNCH = 0, C_PREP = 32, C_Y = 32 * 17, C_W = 32 * 33, C_O = 32 * 41;

#define TSM(cond, slot) do { } while (0)
#define TSIF(cond, slot) do { if (__LINE__ >= FENCE_LO && __LINE__ < FENCE_HI) sched_fence(); } while (0)
__device__ __forceinline__ void sched_fence() {
  asm volatile("{\n.reg .pred p;\n.reg .u32 c;\nmov.u32 c, %%clock;\nsetp.eq.u32 p, c, 0;\n@p st.shared.u32 [%0], c;\n}"
               ::"r"(1024 + OFF_EPOCH + 4) : "memory");
}
#define TS(slot) TSIF(true, slot)

struct Params {
  const __nv_bfloat16 *q, *k, *v, *shift_k, *ssm_k, *ssm_D, *wqkv, *wo, *gate_w;
  __nv_bfloat16* out;
  uint32_t zero;
};

constexpr int SPIN_LIMIT = 1 << 17;

__device__ __forceinline__ void mbar_init(uint32_t bar, uint32_t count) {
  asm volatile("mbarrier.init.shared::cta.b64 [%0], %1;" ::"r"(bar), "r"(count) : "memory");
}
__device__ __forceinline__ void mbar_expect_tx(uint32_t bar, uint32_t bytes) {
  asm volatile("mbarrier.arrive.expect_tx.shared::cta.b64 _, [%0], %1;" ::"r"(bar), "r"(bytes) : "memory");
}
__device__ __forceinline__ void mbar_arrive(uint32_t bar) {
  asm volatile("mbarrier.arrive.shared::cta.b64 _, [%0];" ::"r"(bar) : "memory");
}
__device__ __forceinline__ void mbar_wait(uint32_t bar, uint32_t parity) {
  uint32_t ok;
  int spins = 0;
  do {
      asm volatile("{\n.reg .pred p;\nmbarrier.try_wait.parity.shared::cta.b64 p, [%1], %2;\nselp.b32 %0, 1, 0, p;\n}"
                   : "=r"(ok) : "r"(bar), "r"(parity) : "memory");
    if (++spins > SPIN_LIMIT) break;
  } while (!ok);
}
__device__ __forceinline__ unsigned flag_read(const unsigned* p) {
  unsigned v;
  asm volatile("ld.relaxed.gpu.global.u32 %0, [%1];" : "=r"(v) : "l"(p) : "memory");
  return v;
}
__device__ __forceinline__ void flag_poll(const unsigned* p, unsigned target) {
  unsigned v;
  int spins = 0;
  do {
    asm volatile("ld.relaxed.gpu.global.u32 %0, [%1];" : "=r"(v) : "l"(p) : "memory");
    if (++spins > SPIN_LIMIT) break;
  } while ((int)(v - target) < 0);
}
__device__ __forceinline__ void flag_wait(const unsigned* p, unsigned target) {
  flag_poll(p, target);
}
__device__ __forceinline__ void flag_signal(unsigned* p, int n, int lane) {
  if (lane == 0) asm volatile("fence.release.gpu;" ::: "memory");
  __syncwarp();
  if (lane < n) asm volatile("red.relaxed.gpu.global.add.u32 [%0], 1;" ::"l"(p + 32 * lane) : "memory");
}
__device__ __forceinline__ void flag_bump(unsigned* p) {
  asm volatile("red.relaxed.gpu.global.add.u32 [%0], 1;" ::"l"(p) : "memory");
}
__device__ __forceinline__ void fence_async_smem() { asm volatile("fence.proxy.async.shared::cta;" ::: "memory"); }
__device__ __forceinline__ void wg_sync(int id) { asm volatile("bar.sync %0, 128;" ::"r"(id) : "memory"); }

__device__ __forceinline__ void tma_2d(uint32_t dst, const CUtensorMap* tm, int c0, int c1, uint32_t bar) {
  asm volatile("cp.async.bulk.tensor.2d.shared::cluster.global.mbarrier::complete_tx::bytes [%0], [%1, {%3, %4}], [%2];"
               ::"r"(dst), "l"(tm), "r"(bar), "r"(c0), "r"(c1) : "memory");
}
__device__ __forceinline__ void tma_3d(uint32_t dst, const CUtensorMap* tm, int c0, int c1, int c2, uint32_t bar) {
  asm volatile("cp.async.bulk.tensor.3d.shared::cluster.global.mbarrier::complete_tx::bytes [%0], [%1, {%3, %4, %5}], [%2];"
               ::"r"(dst), "l"(tm), "r"(bar), "r"(c0), "r"(c1), "r"(c2) : "memory");
}
__device__ __forceinline__ void bulk_load(uint32_t dst, const void* src, uint32_t bytes, uint32_t bar) {
  asm volatile("cp.async.bulk.shared::cluster.global.mbarrier::complete_tx::bytes [%0], [%1], %2, [%3];"
               ::"r"(dst), "l"(src), "r"(bytes), "r"(bar) : "memory");
}
__device__ __forceinline__ void bulk_store(void* dst, uint32_t src, uint32_t bytes) {
  asm volatile("cp.async.bulk.global.shared::cta.bulk_group [%0], [%1], %2;" ::"l"(dst), "r"(src), "r"(bytes) : "memory");
}
__device__ __forceinline__ void bulk_wait_read() {
  asm volatile("cp.async.bulk.commit_group;\ncp.async.bulk.wait_group.read 0;" ::: "memory");
}

__device__ __forceinline__ void publish(void* dst, uint32_t src, uint32_t bytes, uint32_t bar) {
  bulk_store(dst, src, bytes);
  bulk_wait_read();
  bulk_load(src, dst, bytes, bar);
}

__device__ __forceinline__ void wg_fence() { asm volatile("wgmma.fence.sync.aligned;" ::: "memory"); }
__device__ __forceinline__ void wg_commit() { asm volatile("wgmma.commit_group.sync.aligned;" ::: "memory"); }
template <int N> __device__ __forceinline__ void wg_wait() { asm volatile("wgmma.wait_group.sync.aligned %0;" ::"n"(N) : "memory"); }
__device__ __forceinline__ uint32_t desc_lo(uint32_t addr, uint32_t lbo) { return ((addr & 0x3FFFF) >> 4) | ((lbo >> 4) << 16); }
constexpr uint32_t desc_hi(uint32_t sbo, uint32_t swz) { return (sbo >> 4) | (swz << 30); }
constexpr uint32_t HI_SW128 = desc_hi(1024, 1), HI_SW64 = desc_hi(512, 2), HI_SW32 = desc_hi(256, 3), HI_NONE = desc_hi(128, 0);
template <int N> __device__ __forceinline__ void pin(float* d) {
#pragma unroll
  for (int i = 0; i < N; i++) asm volatile("" : "+f"(d[i])::"memory");
}

__device__ __forceinline__ uint32_t lds32(uint32_t a) {
  uint32_t v;
  asm volatile("ld.volatile.shared.u32 %0, [%1];" : "=r"(v) : "r"(a) : "memory");
  return v;
}
__device__ __forceinline__ uint2 ldg64(const void* a) {
  uint2 v;
  asm volatile("ld.global.nc.v2.u32 {%0, %1}, [%2];" : "=r"(v.x), "=r"(v.y) : "l"(a) : "memory");
  return v;
}
__device__ __forceinline__ void ldsm4(uint32_t* r, uint32_t a) {
  asm volatile("ldmatrix.sync.aligned.m8n8.x4.shared.b16 {%0, %1, %2, %3}, [%4];"
               : "=r"(r[0]), "=r"(r[1]), "=r"(r[2]), "=r"(r[3]) : "r"(a) : "memory");
}
__device__ __forceinline__ void ldsm4t(uint32_t* r, uint32_t a) {
  asm volatile("ldmatrix.sync.aligned.m8n8.x4.trans.shared.b16 {%0, %1, %2, %3}, [%4];"
               : "=r"(r[0]), "=r"(r[1]), "=r"(r[2]), "=r"(r[3]) : "r"(a) : "memory");
}
__device__ __forceinline__ uint2 lds64(uint32_t a) {
  uint2 v;
  asm volatile("ld.shared.v2.u32 {%0, %1}, [%2];" : "=r"(v.x), "=r"(v.y) : "r"(a) : "memory");
  return v;
}
__device__ __forceinline__ uint4 lds128(uint32_t a) {
  uint4 v;
  asm volatile("ld.shared.v4.u32 {%0, %1, %2, %3}, [%4];" : "=r"(v.x), "=r"(v.y), "=r"(v.z), "=r"(v.w) : "r"(a) : "memory");
  return v;
}
__device__ __forceinline__ void sts128(uint32_t a, uint32_t x, uint32_t y, uint32_t z, uint32_t w) {
  asm volatile("st.shared.v4.u32 [%0], {%1, %2, %3, %4};" ::"r"(a), "r"(x), "r"(y), "r"(z), "r"(w) : "memory");
}
__device__ __forceinline__ void stsm4(uint32_t a, const uint32_t* r) {
  asm volatile("stmatrix.sync.aligned.m8n8.x4.shared.b16 [%0], {%1, %2, %3, %4};" ::"r"(a), "r"(r[0]), "r"(r[1]), "r"(r[2]), "r"(r[3]) : "memory");
}
__device__ __forceinline__ uint32_t pack2(float lo, float hi) {
  uint32_t r;
  asm("cvt.rn.bf16x2.f32 %0, %1, %2;" : "=r"(r) : "f"(hi), "f"(lo));
  return r;
}
__device__ __forceinline__ uint32_t movm(uint32_t a) {
  uint32_t d;
  asm volatile("movmatrix.sync.aligned.m8n8.trans.b16 %0, %1;" : "=r"(d) : "r"(a));
  return d;
}
__device__ __forceinline__ uint32_t bmul(uint32_t a, uint32_t b) {
  uint32_t d;
  asm("mul.rn.bf16x2 %0, %1, %2;" : "=r"(d) : "r"(a), "r"(b));
  return d;
}
__device__ __forceinline__ uint32_t badd(uint32_t a, uint32_t b) {
  uint32_t d;
  asm("add.rn.bf16x2 %0, %1, %2;" : "=r"(d) : "r"(a), "r"(b));
  return d;
}
__device__ __forceinline__ uint32_t bfma(uint32_t a, uint32_t b, uint32_t c) {
  uint32_t d;
  asm("fma.rn.bf16x2 %0, %1, %2, %3;" : "=r"(d) : "r"(a), "r"(b), "r"(c));
  return d;
}
__device__ __forceinline__ float bf_lo(uint32_t x) { return __uint_as_float(x << 16); }
__device__ __forceinline__ float bf_hi(uint32_t x) { return __uint_as_float(x & 0xFFFF0000u); }
__device__ __forceinline__ float ex2(float x) {
  float y;
  asm("ex2.approx.ftz.f32 %0, %1;" : "=f"(y) : "f"(x));
  return y;
}
__device__ __forceinline__ float rcp(float x) {
  float y;
  asm("rcp.approx.ftz.f32 %0, %1;" : "=f"(y) : "f"(x));
  return y;
}
__device__ __forceinline__ void mma16816(float* d, uint32_t a0, uint32_t a1, uint32_t a2, uint32_t a3, uint32_t b0, uint32_t b1) {
  asm volatile("mma.sync.aligned.m16n8k16.row.col.f32.bf16.bf16.f32 {%0, %1, %2, %3}, {%4, %5, %6, %7}, {%8, %9}, {%0, %1, %2, %3};"
               : "+f"(d[0]), "+f"(d[1]), "+f"(d[2]), "+f"(d[3])
               : "r"(a0), "r"(a1), "r"(a2), "r"(a3), "r"(b0), "r"(b1));
}
__device__ __forceinline__ void mma1688(float* d, uint32_t a0, uint32_t a1, uint32_t b0) {
  asm volatile("mma.sync.aligned.m16n8k8.row.col.f32.bf16.bf16.f32 {%0, %1, %2, %3}, {%4, %5}, {%6}, {%0, %1, %2, %3};"
               : "+f"(d[0]), "+f"(d[1]), "+f"(d[2]), "+f"(d[3])
               : "r"(a0), "r"(a1), "r"(b0));
}

template <int N> struct WgRS;
template <int N> struct WgSST;
template <> struct WgRS<32> {
  template <uint32_t HB>
  static __device__ __forceinline__ void mma(float* d, const uint32_t* a, uint32_t db) {
    asm volatile("{\n.reg .pred p;\n.reg .b64 db;\nsetp.ne.b32 p, %22, 0;\n"
      "mov.b64 db, {%20, %21};\n"
      "wgmma.mma_async.sync.aligned.m64n32k16.f32.bf16.bf16 {"
      "%0, %1, %2, %3, %4, %5, %6, %7, %8, %9, %10, %11, %12, %13, %14, %15"
      "}, {%16, %17, %18, %19}, db, p, 1, 1, 1;\n}\n"
      : "+f"(d[0]), "+f"(d[1]), "+f"(d[2]), "+f"(d[3]), "+f"(d[4]), "+f"(d[5]), "+f"(d[6]), "+f"(d[7]),
        "+f"(d[8]), "+f"(d[9]), "+f"(d[10]), "+f"(d[11]), "+f"(d[12]), "+f"(d[13]), "+f"(d[14]), "+f"(d[15])
      : "r"(a[0]), "r"(a[1]), "r"(a[2]), "r"(a[3]), "r"(db), "n"(HB), "n"(1));
  }
  template <uint32_t HB>
  static __device__ __forceinline__ void set(float* d, const uint32_t* a, uint32_t db) {
    asm volatile("{\n.reg .pred p;\n.reg .b64 db;\nsetp.ne.b32 p, %22, 0;\n"
      "mov.b64 db, {%20, %21};\n"
      "wgmma.mma_async.sync.aligned.m64n32k16.f32.bf16.bf16 {"
      "%0, %1, %2, %3, %4, %5, %6, %7, %8, %9, %10, %11, %12, %13, %14, %15"
      "}, {%16, %17, %18, %19}, db, p, 1, 1, 1;\n}\n"
      : "=f"(d[0]), "=f"(d[1]), "=f"(d[2]), "=f"(d[3]), "=f"(d[4]), "=f"(d[5]), "=f"(d[6]), "=f"(d[7]),
        "=f"(d[8]), "=f"(d[9]), "=f"(d[10]), "=f"(d[11]), "=f"(d[12]), "=f"(d[13]), "=f"(d[14]), "=f"(d[15])
      : "r"(a[0]), "r"(a[1]), "r"(a[2]), "r"(a[3]), "r"(db), "n"(HB), "n"(0));
  }
};
template <> struct WgRS<64> {
  template <uint32_t HB>
  static __device__ __forceinline__ void mma(float* d, const uint32_t* a, uint32_t db) {
    asm volatile("{\n.reg .pred p;\n.reg .b64 db;\nsetp.ne.b32 p, %38, 0;\n"
      "mov.b64 db, {%36, %37};\n"
      "wgmma.mma_async.sync.aligned.m64n64k16.f32.bf16.bf16 {"
      "%0, %1, %2, %3, %4, %5, %6, %7, %8, %9, %10, %11, %12, %13, %14, %15, "
      "%16, %17, %18, %19, %20, %21, %22, %23, %24, %25, %26, %27, %28, %29, %30, %31"
      "}, {%32, %33, %34, %35}, db, p, 1, 1, 1;\n}\n"
      : "+f"(d[0]), "+f"(d[1]), "+f"(d[2]), "+f"(d[3]), "+f"(d[4]), "+f"(d[5]), "+f"(d[6]), "+f"(d[7]),
        "+f"(d[8]), "+f"(d[9]), "+f"(d[10]), "+f"(d[11]), "+f"(d[12]), "+f"(d[13]), "+f"(d[14]), "+f"(d[15]),
        "+f"(d[16]), "+f"(d[17]), "+f"(d[18]), "+f"(d[19]), "+f"(d[20]), "+f"(d[21]), "+f"(d[22]), "+f"(d[23]),
        "+f"(d[24]), "+f"(d[25]), "+f"(d[26]), "+f"(d[27]), "+f"(d[28]), "+f"(d[29]), "+f"(d[30]), "+f"(d[31])
      : "r"(a[0]), "r"(a[1]), "r"(a[2]), "r"(a[3]), "r"(db), "n"(HB), "n"(1));
  }
  template <uint32_t HB>
  static __device__ __forceinline__ void set(float* d, const uint32_t* a, uint32_t db) {
    asm volatile("{\n.reg .pred p;\n.reg .b64 db;\nsetp.ne.b32 p, %38, 0;\n"
      "mov.b64 db, {%36, %37};\n"
      "wgmma.mma_async.sync.aligned.m64n64k16.f32.bf16.bf16 {"
      "%0, %1, %2, %3, %4, %5, %6, %7, %8, %9, %10, %11, %12, %13, %14, %15, "
      "%16, %17, %18, %19, %20, %21, %22, %23, %24, %25, %26, %27, %28, %29, %30, %31"
      "}, {%32, %33, %34, %35}, db, p, 1, 1, 1;\n}\n"
      : "=f"(d[0]), "=f"(d[1]), "=f"(d[2]), "=f"(d[3]), "=f"(d[4]), "=f"(d[5]), "=f"(d[6]), "=f"(d[7]),
        "=f"(d[8]), "=f"(d[9]), "=f"(d[10]), "=f"(d[11]), "=f"(d[12]), "=f"(d[13]), "=f"(d[14]), "=f"(d[15]),
        "=f"(d[16]), "=f"(d[17]), "=f"(d[18]), "=f"(d[19]), "=f"(d[20]), "=f"(d[21]), "=f"(d[22]), "=f"(d[23]),
        "=f"(d[24]), "=f"(d[25]), "=f"(d[26]), "=f"(d[27]), "=f"(d[28]), "=f"(d[29]), "=f"(d[30]), "=f"(d[31])
      : "r"(a[0]), "r"(a[1]), "r"(a[2]), "r"(a[3]), "r"(db), "n"(HB), "n"(0));
  }
};
template <> struct WgSST<48> {
  template <uint32_t HA, uint32_t HB>
  static __device__ __forceinline__ void mma(float* d, uint32_t da, uint32_t db, int sc) {
    asm volatile("{\n.reg .pred p;\n.reg .b64 da, db;\nsetp.ne.b32 p, %28, 0;\n"
      "mov.b64 da, {%24, %25};\nmov.b64 db, {%26, %27};\n"
      "wgmma.mma_async.sync.aligned.m64n48k16.f32.bf16.bf16 {"
      "%0, %1, %2, %3, %4, %5, %6, %7, %8, %9, %10, %11, %12, %13, %14, %15, "
      "%16, %17, %18, %19, %20, %21, %22, %23"
      "}, da, db, p, 1, 1, 0, 1;\n}\n"
      : "+f"(d[0]), "+f"(d[1]), "+f"(d[2]), "+f"(d[3]), "+f"(d[4]), "+f"(d[5]), "+f"(d[6]), "+f"(d[7]),
        "+f"(d[8]), "+f"(d[9]), "+f"(d[10]), "+f"(d[11]), "+f"(d[12]), "+f"(d[13]), "+f"(d[14]), "+f"(d[15]),
        "+f"(d[16]), "+f"(d[17]), "+f"(d[18]), "+f"(d[19]), "+f"(d[20]), "+f"(d[21]), "+f"(d[22]), "+f"(d[23])
      : "r"(da), "n"(HA), "r"(db), "n"(HB), "r"(sc));
  }
};
template <> struct WgSST<80> {
  template <uint32_t HA, uint32_t HB>
  static __device__ __forceinline__ void mma(float* d, uint32_t da, uint32_t db, int sc) {
    asm volatile("{\n.reg .pred p;\n.reg .b64 da, db;\nsetp.ne.b32 p, %44, 0;\n"
      "mov.b64 da, {%40, %41};\nmov.b64 db, {%42, %43};\n"
      "wgmma.mma_async.sync.aligned.m64n80k16.f32.bf16.bf16 {"
      "%0, %1, %2, %3, %4, %5, %6, %7, %8, %9, %10, %11, %12, %13, %14, %15, "
      "%16, %17, %18, %19, %20, %21, %22, %23, %24, %25, %26, %27, %28, %29, %30, %31, "
      "%32, %33, %34, %35, %36, %37, %38, %39"
      "}, da, db, p, 1, 1, 0, 1;\n}\n"
      : "+f"(d[0]), "+f"(d[1]), "+f"(d[2]), "+f"(d[3]), "+f"(d[4]), "+f"(d[5]), "+f"(d[6]), "+f"(d[7]),
        "+f"(d[8]), "+f"(d[9]), "+f"(d[10]), "+f"(d[11]), "+f"(d[12]), "+f"(d[13]), "+f"(d[14]), "+f"(d[15]),
        "+f"(d[16]), "+f"(d[17]), "+f"(d[18]), "+f"(d[19]), "+f"(d[20]), "+f"(d[21]), "+f"(d[22]), "+f"(d[23]),
        "+f"(d[24]), "+f"(d[25]), "+f"(d[26]), "+f"(d[27]), "+f"(d[28]), "+f"(d[29]), "+f"(d[30]), "+f"(d[31]),
        "+f"(d[32]), "+f"(d[33]), "+f"(d[34]), "+f"(d[35]), "+f"(d[36]), "+f"(d[37]), "+f"(d[38]), "+f"(d[39])
      : "r"(da), "n"(HA), "r"(db), "n"(HB), "r"(sc));
  }
};
template <> struct WgSST<192> {
  template <uint32_t HA, uint32_t HB>
  static __device__ __forceinline__ void mma(float* d, uint32_t da, uint32_t db, int sc) {
    asm volatile("{\n.reg .pred p;\n.reg .b64 da, db;\nsetp.ne.b32 p, %100, 0;\n"
      "mov.b64 da, {%96, %97};\nmov.b64 db, {%98, %99};\n"
      "wgmma.mma_async.sync.aligned.m64n192k16.f32.bf16.bf16 {"
      "%0, %1, %2, %3, %4, %5, %6, %7, %8, %9, %10, %11, %12, %13, %14, %15, "
      "%16, %17, %18, %19, %20, %21, %22, %23, %24, %25, %26, %27, %28, %29, %30, %31, "
      "%32, %33, %34, %35, %36, %37, %38, %39, %40, %41, %42, %43, %44, %45, %46, %47, "
      "%48, %49, %50, %51, %52, %53, %54, %55, %56, %57, %58, %59, %60, %61, %62, %63, "
      "%64, %65, %66, %67, %68, %69, %70, %71, %72, %73, %74, %75, %76, %77, %78, %79, "
      "%80, %81, %82, %83, %84, %85, %86, %87, %88, %89, %90, %91, %92, %93, %94, %95"
      "}, da, db, p, 1, 1, 0, 1;\n}\n"
      : "+f"(d[0]), "+f"(d[1]), "+f"(d[2]), "+f"(d[3]), "+f"(d[4]), "+f"(d[5]), "+f"(d[6]), "+f"(d[7]),
        "+f"(d[8]), "+f"(d[9]), "+f"(d[10]), "+f"(d[11]), "+f"(d[12]), "+f"(d[13]), "+f"(d[14]), "+f"(d[15]),
        "+f"(d[16]), "+f"(d[17]), "+f"(d[18]), "+f"(d[19]), "+f"(d[20]), "+f"(d[21]), "+f"(d[22]), "+f"(d[23]),
        "+f"(d[24]), "+f"(d[25]), "+f"(d[26]), "+f"(d[27]), "+f"(d[28]), "+f"(d[29]), "+f"(d[30]), "+f"(d[31]),
        "+f"(d[32]), "+f"(d[33]), "+f"(d[34]), "+f"(d[35]), "+f"(d[36]), "+f"(d[37]), "+f"(d[38]), "+f"(d[39]),
        "+f"(d[40]), "+f"(d[41]), "+f"(d[42]), "+f"(d[43]), "+f"(d[44]), "+f"(d[45]), "+f"(d[46]), "+f"(d[47]),
        "+f"(d[48]), "+f"(d[49]), "+f"(d[50]), "+f"(d[51]), "+f"(d[52]), "+f"(d[53]), "+f"(d[54]), "+f"(d[55]),
        "+f"(d[56]), "+f"(d[57]), "+f"(d[58]), "+f"(d[59]), "+f"(d[60]), "+f"(d[61]), "+f"(d[62]), "+f"(d[63]),
        "+f"(d[64]), "+f"(d[65]), "+f"(d[66]), "+f"(d[67]), "+f"(d[68]), "+f"(d[69]), "+f"(d[70]), "+f"(d[71]),
        "+f"(d[72]), "+f"(d[73]), "+f"(d[74]), "+f"(d[75]), "+f"(d[76]), "+f"(d[77]), "+f"(d[78]), "+f"(d[79]),
        "+f"(d[80]), "+f"(d[81]), "+f"(d[82]), "+f"(d[83]), "+f"(d[84]), "+f"(d[85]), "+f"(d[86]), "+f"(d[87]),
        "+f"(d[88]), "+f"(d[89]), "+f"(d[90]), "+f"(d[91]), "+f"(d[92]), "+f"(d[93]), "+f"(d[94]), "+f"(d[95])
      : "r"(da), "n"(HA), "r"(db), "n"(HB), "r"(sc));
  }
};

struct FftConst {
  uint32_t f[2][4], fi[4][4];
  uint32_t ta[2][2], tb[2][2];
};
__device__ __forceinline__ void cis(int m, float scale, float& c, float& s) {
  const float a = (float)m * (-6.283185307179586f * scale);
  c = __cosf(a);
  s = __sinf(a);
}
__device__ __forceinline__ void fft_tables(uint32_t (&v)[12], int tw) {
  const int row = tw >> 2, ch = tw & 3;
#pragma unroll
  for (int i = 0; i < 4; i++) {
    float c[2], s[2], x[2];
#pragma unroll
    for (int e = 0; e < 2; e++) {
      cis((((32 * (8 * ch + 2 * i + e) + 15) * (4 * row - 63) + 2048) & 4095) - 2048, 1.f / 4096, c[e], s[e]);
      float gc, gs;
      cis((((row & 15) * (8 * (ch & 1) + 2 * i + e) + 8) & 15) - 8, 1.f / 16, gc, gs);
      x[e] = (row >> 4) == (ch >> 1) ? gc : (ch >> 1) ? gs : -gs;
    }
    v[i] = pack2(c[0] * 0.125f, c[1] * 0.125f);
    v[4 + i] = pack2(s[0] * 0.125f, s[1] * 0.125f);
    v[8 + i] = pack2(x[0], x[1]);
  }
#pragma unroll
  for (int i = 0; i < 12; i++) asm volatile("" : "+r"(v[i]));
}
__device__ __forceinline__ void fft_tables_store(const uint32_t (&v)[12], uint32_t sb, int tw) {
  const int row = tw >> 2;
  const uint32_t x = ((tw ^ (row >> 1)) & 3) << 4, a = sb + OFF_FT + (16 * (row >> 3) + (row & 7)) * 64 + x;
  sts128(a, v[0], v[1], v[2], v[3]);
  sts128(a + 512, v[4], v[5], v[6], v[7]);
  sts128(sb + OFF_GT + row * 64 + x, v[8], v[9], v[10], v[11]);
}
__device__ __forceinline__ void fft_twiddles(uint32_t (&v)[2], int tw) {
  float a[2], s[2];
#pragma unroll
  for (int i = 0; i < 2; i++) {
    float c;
    cis((2 * (2 * (tw & 3) + i) - 15) * (4 * (tw >> 2) - 63), 1.f / 4096, c, s[i]);
    a[i] = __fdividef(-s[i], 1.f + c);
  }
  v[0] = pack2(a[0], a[1]);
  v[1] = pack2(s[0], s[1]);
  asm volatile("" : "+r"(v[0]), "+r"(v[1]));
}
__device__ __forceinline__ void fft_matrices(FftConst& k, uint32_t sb, int w, int lane) {
  const uint32_t x = (lane >> 1) & 3;
  const uint2 t0 = lds64(sb + OFF_TT + 256 * w + 8 * lane), t1 = lds64(sb + OFF_TT + 256 * w + 8 * (lane ^ 3));
  k.ta[0][0] = t0.x;
  k.tb[0][0] = t0.y;
  k.ta[1][1] = __byte_perm(t1.x, 0, 0x1032);
  k.tb[1][1] = __byte_perm(t1.y, 0, 0x1032);
#pragma unroll
  for (int j = 0; j < 2; j++) {
    k.ta[1 - j][j] = k.ta[j][j] ^ 0x80008000u;
    k.tb[1 - j][j] = k.tb[j][j] ^ 0x80008000u;
    asm volatile("" : "+r"(k.ta[0][j]), "+r"(k.tb[0][j]), "+r"(k.ta[1][j]), "+r"(k.tb[1][j]));
  }
#pragma unroll
  for (int i = 0; i < 2; i++) {
    ldsm4(k.f[i], sb + OFF_FT + (16 * w + (lane & 15)) * 64 + (((2 * i + (lane >> 4)) ^ x) << 4));
    ldsm4t(k.fi[i], sb + OFF_FT + (32 * i + lane) * 64 + ((w ^ x) << 4));
#pragma unroll
    for (int j = 0; j < 4; j++) {
      k.fi[2 + i][j] = (j & 1) ? k.fi[i][j - 1] ^ 0x80008000u : k.fi[i][j + 1];
      asm volatile("" : "+r"(k.fi[2 + i][j]));
    }
  }
}
__device__ __forceinline__ void rot(uint32_t& x, uint32_t& y, uint32_t a, uint32_t b) {
  x = bfma(a, y, x);
  y = bfma(b, x, y);
  x = bfma(a, y, x);
}
__device__ __forceinline__ void twiddle_fwd(uint32_t (&a)[4][4], float* d, const FftConst& k) {
#pragma unroll
  for (int q = 0; q < 4; q++)
#pragma unroll
    for (int j = 0; j < 2; j++) {
      const float* x = d + 8 * q + 4 * j;
      uint32_t re = pack2(x[0], x[1]), im = pack2(x[2], x[3]);
      rot(re, im, k.ta[0][j], k.tb[0][j]);
      a[q & 2][2 * j + (q & 1)] = re;
      a[(q & 2) + 1][2 * j + (q & 1)] = im;
    }
}
__device__ __forceinline__ void g_step(float* d, const uint32_t (&a)[4][4], uint32_t dre, uint32_t dim) {
  WgRS<32>::set<HI_SW64>(d, a[0], dre);
  WgRS<32>::set<HI_SW64>(d + 16, a[2], dre);
  WgRS<32>::mma<HI_SW64>(d, a[1], dim);
  WgRS<32>::mma<HI_SW64>(d + 16, a[3], dim);
  wg_commit();
}

__device__ __forceinline__ void products(uint32_t (&a)[4][4], const float* H, const float* U, int p) {
#pragma unroll
  for (int j = 0; j < 2; j++)
#pragma unroll
    for (int m = 2 * p; m < 2 * p + 2; m++) {
      float pr[2], pi[2];
#pragma unroll
      for (int x = 0; x < 2; x++)
#pragma unroll
        for (int q = 0; q <= m; q++) {
          const int ih = 16 * (q >> 1) + 2 * (q & 1) + 4 * j + x, iu = 16 * ((m - q) >> 1) + 2 * ((m - q) & 1) + 4 * j + x;
          pr[x] = q ? fmaf(H[ih], U[iu], pr[x]) : H[ih] * U[iu];
          pi[x] = q ? fmaf(H[ih], U[iu + 8], pi[x]) : H[ih] * U[iu + 8];
          pr[x] = fmaf(-H[ih + 8], U[iu + 8], pr[x]);
          pi[x] = fmaf(H[ih + 8], U[iu], pi[x]);
        }
      a[m & 2][2 * j + (m & 1)] = pack2(pr[0], pr[1]);
      a[(m & 2) + 1][2 * j + (m & 1)] = pack2(pi[0], pi[1]);
    }
}

__device__ __forceinline__ void conv_channel(const FftConst& k, uint32_t sb, int c, int wg, int w, int lane) {
  const uint32_t cb = sb + off_ch(c), bars = sb + OFF_BAR;
  const uint32_t du = desc_lo(cb, 1024), dg = desc_lo(sb + OFF_GT, 16), dz = desc_lo(cb, 16);
  float U[32], H[32];
  uint32_t a[4][4], e[4][4];
  const float dv = __uint_as_float(lds32(sb + OFF_D + 4 * c));
  wg_fence();
  WgRS<64>::set<HI_SW32>(H, k.f[0], du + 256);
  WgRS<64>::mma<HI_SW32>(H, k.f[1], du + 256 + 32);
  wg_commit();
  wg_wait<0>();
  pin<32>(H);
  twiddle_fwd(a, H, k);
  mbar_wait(bars + 8 * (B_U + (c < 3 ? c : 3)), 0);
  TSM(w == 0 && c < 3, 7 + wg);
  wg_fence();
  WgRS<64>::set<HI_SW32>(U, k.f[0], du);
  WgRS<64>::mma<HI_SW32>(U, k.f[1], du + 32);
  wg_commit();
  g_step(H, a, dg, dg + 64);
  wg_wait<1>();
  pin<32>(U);
  twiddle_fwd(e, U, k);
  wg_fence();
  g_step(U, e, dg, dg + 64);
  wg_wait<0>();
  pin<32>(U);
  pin<32>(H);
#pragma unroll
  for (int j = 0; j < 4; j++) H[4 * (j >> 1) + (j & 1)] += dv;
  float V[32];
#pragma unroll
  for (int p = 0; p < 2; p++) {
    products(a, H, U, p);
    wg_fence();
    WgRS<32>::set<HI_SW64>(V + 16 * p, a[2 * p], dg + 64);
    WgRS<32>::mma<HI_SW64>(V + 16 * p, a[2 * p + 1], dg);
    wg_commit();
  }
  const uint32_t za = cb + (8 * w + (lane & 7)) * 128 + (((lane >> 3) ^ (lane & 7)) << 4);
  const uint32_t ya = cb + (lane >> 4) * 1024 + (8 * w + (lane & 7)) * 32 + ((((lane >> 3) ^ (lane >> 2)) & 1) << 4);
  wg_sync(1 + wg);
#pragma unroll
  for (int p = 0; p < 2; p++) {
    if (p == 0) wg_wait<1>();
    else wg_wait<0>();
    pin<16>(V + 16 * p);
#pragma unroll
    for (int i = 0; i < 4; i++) {
      const int j = i & 1;
      const float* x = V + 16 * p + 4 * j + (i & 2);
      e[p][i] = pack2(x[8], x[9]);
      e[2 + p][i] = pack2(x[0], x[1]);
      rot(e[p][i], e[2 + p][i], k.ta[1][j], k.tb[1][j]);
    }
    stsm4(za ^ (64 * p), e[p]);
    stsm4((za ^ (64 * p)) + 4096, e[2 + p]);
  }
  fence_async_smem();
  wg_sync(1 + wg);
  wg_fence();
  WgRS<64>::set<HI_SW128>(H, k.fi[0], dz);
#pragma unroll
  for (int ks = 1; ks < 4; ks++) WgRS<64>::mma<HI_SW128>(H, k.fi[ks], dz + 128 * ks);
  wg_commit();
  wg_wait<0>();
  pin<32>(H);
  if (lane == 0) mbar_arrive(bars + 8 * B_CVD);
  TSIF(w == 0, 88 + c);
#pragma unroll
  for (int j = 0; j < 8; j++)
    a[j >> 2][j & 3] = j < 2 ? pack2(H[4 * j], H[4 * j + 1]) : pack2(H[4 * j] + H[4 * j - 6], H[4 * j + 1] + H[4 * j - 5]);
  wg_sync(1 + wg);
  stsm4(ya, a[0]);
  stsm4(ya + 2048, a[1]);
  fence_async_smem();
  __syncwarp();
}

__device__ __forceinline__ void prep_slab(uint4* res, const uint2* sw, uint32_t sb, int slab, int w, int lane) {
  const int t = lane & 3, tp = (lane & 7) >> 1, pos = 8 * tp + 2 * (((lane >> 3) + tp) & 3) + (lane & 1);
  const uint32_t base = sb + OFF_KVS + slab * KVS_BYTES + pos * 128;
  uint32_t kk[2][4][4], vv[2][4];
  mbar_wait(sb + OFF_BAR + 8 * (B_KV + slab), 0);
#pragma unroll
  for (int h = 0; h < 2; h++) {
#pragma unroll
    for (int j = 0; j < 4; j++) {
      const uint32_t a = base + 128 * j;
      ldsm4t(kk[h][j], a + (((w + 4 * h) ^ ((a >> 7) & 7)) << 4));
    }
    const uint32_t a = base + KVS_V;
    ldsm4t(vv[h], a + (((w + 4 * h) ^ ((a >> 7) & 7)) << 4));
  }
#pragma unroll
  for (int h = 0; h < 2; h++) {
    uint32_t (&k)[4][4] = kk[h];
    uint32_t (&v)[4] = vv[h];
    const uint32_t w0 = __byte_perm(sw[h].x, 0, 0x1010), w1 = __byte_perm(sw[h].x, 0, 0x3232);
    const uint32_t w2 = __byte_perm(sw[h].y, 0, 0x1010), w3 = __byte_perm(sw[h].y, 0, 0x3232);
#pragma unroll
    for (int m = 0; m < 4; m++)
      v[m] = bmul(badd(badd(badd(bmul(k[0][m], w3), bmul(k[1][m], w2)), bmul(k[2][m], w1)), bmul(k[3][m], w0)), v[m]);
    uint32_t a[4];
#pragma unroll
    for (int m = 0; m < 4; m++) a[m] = (t & 1) ? v[(m + 3) & 3] : v[m];
    res[h] = (t & 2) ? make_uint4(a[2], a[3], a[0], a[1]) : make_uint4(a[0], a[1], a[2], a[3]);
  }
}

__device__ __forceinline__ void prep_gate(const Params& p, uint32_t sb, int b, int w, int lane) {
  uint2 gw[5], x[4][5];
#pragma unroll
  for (int j = 0; j < 5; j++) gw[j] = ldg64(reinterpret_cast<const uint2*>(p.gate_w) + lane + 32 * j);
#pragma unroll
  for (int i = 0; i < 4; i++)
#pragma unroll
    for (int j = 0; j < 5; j++)
      x[i][j] = ldg64(reinterpret_cast<const uint2*>(p.q) + (16 * b + 4 * w + i) * (DIM / 4) + lane + 32 * j);
  float s[4];
#pragma unroll
  for (int i = 0; i < 4; i++) {
    s[i] = 0.f;
#pragma unroll
    for (int j = 0; j < 5; j++) {
      const uint32_t m0 = bmul(x[i][j].x, gw[j].x), m1 = bmul(x[i][j].y, gw[j].y);
      s[i] += (bf_lo(m0) + bf_hi(m0)) + (bf_lo(m1) + bf_hi(m1));
    }
  }
  const bool h = lane & 16, q = lane & 8;
  const float a = (h ? s[2] : s[0]) + __shfl_xor_sync(0xffffffffu, h ? s[0] : s[2], 16);
  const float c = (h ? s[3] : s[1]) + __shfl_xor_sync(0xffffffffu, h ? s[1] : s[3], 16);
  float z = (q ? c : a) + __shfl_xor_sync(0xffffffffu, q ? a : c, 8);
#pragma unroll
  for (int o = 4; o > 0; o >>= 1) z += __shfl_xor_sync(0xffffffffu, z, o);
  z = bf_lo(pack2(z, 0.f));
  z = bf_lo(pack2(__fdividef(1.f, 1.f + __expf(-z)), 0.f));
  mbar_wait(sb + OFF_BAR + 8 * B_S3, 0);
  if ((lane & 7) == 0) asm volatile("st.shared.f32 [%0], %1;" ::"r"(sb + OFF_GATE + 64 * (b & 7) + 16 * w + (lane >> 1)), "f"(z) : "memory");
  fence_async_smem();
}

__device__ __forceinline__ uint32_t bmax(uint32_t a, uint32_t b) {
  uint32_t d;
  asm("max.bf16x2 %0, %1, %2;" : "=r"(d) : "r"(a), "r"(b));
  return d;
}
__device__ __forceinline__ void softmax_two(const float (&l)[2][2], uint32_t& p0, uint32_t& p1) {
  constexpr float kScale = 0.22360679774997896f, kLog2e = 1.4426950408889634f;
  const uint32_t r0 = pack2(l[0][0], l[1][0]), r1 = pack2(l[0][1], l[1][1]);
  const uint32_t x0 = pack2(bf_lo(r0) * kScale, bf_hi(r0) * kScale), x1 = pack2(bf_lo(r1) * kScale, bf_hi(r1) * kScale);
  uint32_t m = bmax(x0, x1);
  m = bmax(m, __shfl_xor_sync(0xffffffffu, m, 1));
  m = bmax(m, __shfl_xor_sync(0xffffffffu, m, 2));
  const float m0 = bf_lo(m) * kLog2e, m1 = bf_hi(m) * kLog2e;
  p0 = pack2(ex2(bf_lo(x0) * kLog2e - m0), ex2(bf_lo(x1) * kLog2e - m0));
  p1 = pack2(ex2(bf_hi(x0) * kLog2e - m1), ex2(bf_hi(x1) * kLog2e - m1));
}

__device__ __forceinline__ void halo_read(uint32_t (&kpv)[10], uint32_t (&vpv)[10], uint32_t (&tg)[7], const uint4* hp) {
#pragma unroll
  for (int j = 0; j < 7; j++) {
    uint32_t x0, x1, x2;
    asm volatile("ld.relaxed.gpu.global.v4.u32 {%0, %1, %2, %3}, [%4];"
                 : "=r"(x0), "=r"(x1), "=r"(x2), "=r"(tg[j]) : "l"(hp + 32 * j) : "memory");
    if (j < 4) kpv[3 * j] = x0; else vpv[3 * j - 10] = x0;
    if (j < 3) kpv[3 * j + 1] = x1; else vpv[3 * j - 9] = x1;
    if (j < 3) kpv[3 * j + 2] = x2; else if (j < 6) vpv[3 * j - 8] = x2;
  }
}

template <int ROT>
__device__ __forceinline__ void pack_qkv(const float* acc, uint32_t (&qlo)[10], uint32_t (&qhi)[10], uint32_t (&klo)[10],
                                         uint32_t (&khi)[10], uint32_t (&vlo)[10], uint32_t (&vhi)[10]) {
#pragma unroll
  for (int j = 0; j < 10; j++) {
    const int x = (j + ROT) % 10, tq = x < 8 ? x : 16 + x, tk = x < 8 ? 8 + x : 18 + x, tv = x < 8 ? 16 + x : 20 + x;
    khi[j] = pack2(acc[4 * tk + 2], acc[4 * tk + 3]);
    vhi[j] = movm(pack2(acc[4 * tv + 2], acc[4 * tv + 3]));
    qlo[j] = pack2(acc[4 * tq], acc[4 * tq + 1]);
    qhi[j] = pack2(acc[4 * tq + 2], acc[4 * tq + 3]);
    klo[j] = pack2(acc[4 * tk], acc[4 * tk + 1]);
    vlo[j] = pack2(acc[4 * tv], acc[4 * tv + 1]);
    asm volatile("" : "+r"(khi[j]), "+r"(qlo[j]), "+r"(qhi[j]), "+r"(klo[j]), "+r"(vlo[j]));
  }
}

template <int ROT> __device__ __forceinline__ void halo_send(const float* acc, uint4* ho, uint32_t tag) {
#pragma unroll
  for (int j = 0; j < 7; j++) {
    uint32_t x[3];
#pragma unroll
    for (int e = 0; e < 3; e++) {
      const int i = 3 * j + e, y = (i % 10 + ROT) % 10, tk = y < 8 ? 8 + y : 18 + y, tv = y < 8 ? 16 + y : 20 + y;
      x[e] = i < 10 ? pack2(acc[4 * tk + 2], acc[4 * tk + 3]) : i < 20 ? movm(pack2(acc[4 * tv + 2], acc[4 * tv + 3])) : 0u;
    }
    asm volatile("st.relaxed.gpu.global.v4.u32 [%0], {%1, %2, %3, %4};" ::"l"(ho + 32 * j), "r"(x[0]), "r"(x[1]), "r"(x[2]), "r"(tag) : "memory");
  }
}

__device__ __forceinline__ void attention(float* acc, uint32_t sb, int b, int par, int w, int lane, uint32_t tag) {
  const int g = lane >> 2, t = lane & 3;
  uint32_t klo[10], khi[10], vlo[10], vhi[10], qlo[10], qhi[10], kpv[10], vpv[10];
  if (w == 3 && b < NCTA - 8) {
    uint4* ho = g_halo + (b * 2 + par) * 224 + lane;
    if (tail_first(b & 7)) halo_send<8>(acc, ho, tag);
    else halo_send<0>(acc, ho, tag);
    TSIF(par == 0, 76);
    pin<120>(acc);
  }
  if (tail_first(b & 7)) pack_qkv<8>(acc, qlo, qhi, klo, khi, vlo, vhi);
  else pack_qkv<0>(acc, qlo, qhi, klo, khi, vlo, vhi);
  const uint32_t xa = sb + OFF_KVX + (par * 3) * 2560 + lane * 16;
  if (w < 3) {
    sts128(xa + w * 2560, khi[0], khi[1], khi[2], khi[3]);
    sts128(xa + w * 2560 + 512, khi[4], khi[5], khi[6], khi[7]);
    sts128(xa + w * 2560 + 1024, khi[8], khi[9], vhi[0], vhi[1]);
    sts128(xa + w * 2560 + 1536, vhi[2], vhi[3], vhi[4], vhi[5]);
    sts128(xa + w * 2560 + 2048, vhi[6], vhi[7], vhi[8], vhi[9]);
  }
  TSIF(par == 0 && w == 1, 64);
#pragma unroll
  for (int j = 0; j < 10; j++) vlo[j] = movm(vlo[j]);
  const bool far0 = 2 * t > g, far1 = 2 * t + 1 > g;
  const uint32_t mfar = (far0 ? 0x0000FFFFu : 0u) | (far1 ? 0xFFFF0000u : 0u);
  float slo[4][2], lg[2][2];
  uint32_t phi[4], plo[4], qml[4], qmh[4];
#pragma unroll
  for (int h = 0; h < 4; h++) {
    const int f = h == 0 ? 0 : h == 1 ? 3 : h == 2 ? 5 : 8, hf = h < 2 ? 2 : 7;
    const bool mine = (h & 1) ? t >= 2 : t < 2;
    qml[h] = mine ? qlo[hf] : 0u;
    qmh[h] = mine ? qhi[hf] : 0u;
    float a[4] = {0.f, 0.f, 0.f, 0.f}, c[4] = {0.f, 0.f, 0.f, 0.f};
    mma16816(a, qlo[f], qhi[f], qlo[f + 1], qhi[f + 1], klo[f], klo[f + 1]);
    mma16816(c, qlo[f], qhi[f], qlo[f + 1], qhi[f + 1], khi[f], khi[f + 1]);
    mma1688(a, qml[h], qmh[h], klo[hf]);
    mma1688(c, qml[h], qmh[h], khi[hf]);
    slo[h][0] = a[0];
    slo[h][1] = a[1];
    lg[h & 1][0] = far0 ? a[2] : c[2];
    lg[h & 1][1] = far1 ? a[3] : c[3];
    if (h & 1) softmax_two(lg, phi[h - 1], phi[h]);
  }
  TSIF(par == 0 && w == 1, 65);
  wg_sync(1 + par);
  TSIF(par == 0 && w == 1, 66);
  const bool nohist = (w == 0) && (b < 8);
  const uint4* hp = g_halo + ((b - 8) * 2 + par) * 224 + lane;
  uint32_t tg[7];
  if (w > 0) {
    const uint4 v0 = lds128(xa + (w - 1) * 2560), v1 = lds128(xa + (w - 1) * 2560 + 512), v2 = lds128(xa + (w - 1) * 2560 + 1024);
    const uint4 v3 = lds128(xa + (w - 1) * 2560 + 1536), v4 = lds128(xa + (w - 1) * 2560 + 2048);
    kpv[0] = v0.x; kpv[1] = v0.y; kpv[2] = v0.z; kpv[3] = v0.w; kpv[4] = v1.x; kpv[5] = v1.y; kpv[6] = v1.z; kpv[7] = v1.w;
    kpv[8] = v2.x; kpv[9] = v2.y; vpv[0] = v2.z; vpv[1] = v2.w; vpv[2] = v3.x; vpv[3] = v3.y; vpv[4] = v3.z; vpv[5] = v3.w;
    vpv[6] = v4.x; vpv[7] = v4.y; vpv[8] = v4.z; vpv[9] = v4.w;
  } else if (nohist) {
#pragma unroll
    for (int j = 0; j < 10; j++) kpv[j] = vpv[j] = 0u;
  } else {
    TSIF(par == 0, 77);
    halo_read(kpv, vpv, tg, hp);
  }
  if (w == 0 && !nohist) {
    int spins = 0;
    while (true) {
      bool ok = true;
#pragma unroll
      for (int j = 0; j < 7; j++) ok = ok && tg[j] == tag;
      if (__all_sync(0xffffffffu, ok) || ++spins > SPIN_LIMIT) break;
      halo_read(kpv, vpv, tg, hp);
    }
    TSIF(par == 0, 79);
  }
#pragma unroll
  for (int h = 0; h < 4; h++) {
    const int f = h == 0 ? 0 : h == 1 ? 3 : h == 2 ? 5 : 8, hf = h < 2 ? 2 : 7;
    float a[4] = {0.f, 0.f, 0.f, 0.f};
    mma16816(a, qlo[f], qhi[f], qlo[f + 1], qhi[f + 1], kpv[f], kpv[f + 1]);
    mma1688(a, qml[h], qmh[h], kpv[hf]);
    const float ninf = __int_as_float(0xff800000);
    lg[h & 1][0] = far0 ? (nohist ? ninf : a[0]) : slo[h][0];
    lg[h & 1][1] = far1 ? (nohist ? ninf : a[1]) : slo[h][1];
    if (h & 1) softmax_two(lg, plo[h - 1], plo[h]);
  }
  TSIF(par == 0 && w <= 1, 67 + w);
  uint32_t ov[20];
#pragma unroll
  for (int hp = 0; hp < 2; hp++) {
    const int hf = hp ? 7 : 2;
    float sh[4] = {0.f, 0.f, 0.f, 0.f}, i0 = 0.f, i1 = 0.f;
#pragma unroll
    for (int e = 0; e < 2; e++) {
      const int h = 2 * hp + e, f = h == 0 ? 0 : h == 1 ? 3 : h == 2 ? 5 : 8;
      const uint32_t a0 = plo[h] & mfar, a2 = plo[h] & ~mfar, a3 = phi[h] & mfar, c1 = phi[h] & ~mfar;
      float sum[4] = {0.f, 0.f, 0.f, 0.f};
      mma1688(sum, plo[h], phi[h], 0x3F803F80u);
      const float r0 = rcp(sum[0]), r1 = rcp(sum[2]);
#pragma unroll
      for (int j = f; j < f + 2; j++) {
        float o[4] = {0.f, 0.f, 0.f, 0.f};
        mma16816(o, a0, 0u, a2, a3, vpv[j], vlo[j]);
        mma1688(o, 0u, c1, vhi[j]);
        ov[2 * j] = pack2(o[0] * r0, o[1] * r0);
        ov[2 * j + 1] = pack2(o[2] * r1, o[3] * r1);
      }
      const bool mine = e ? g >= 4 : g < 4;
      mma16816(sh, a0, 0u, a2, a3, mine ? vpv[hf] : 0u, mine ? vlo[hf] : 0u);
      mma1688(sh, 0u, c1, mine ? vhi[hf] : 0u);
      if (e == 0 || t >= 2) {
        i0 = r0;
        i1 = r1;
      }
    }
    ov[2 * hf] = pack2(sh[0] * i0, sh[1] * i0);
    ov[2 * hf + 1] = pack2(sh[2] * i1, sh[3] * i1);
  }
  TS(32 + 4 * par + w);
  mbar_wait(sb + OFF_BAR + 8 * B_P1, 0);
  const uint32_t oa = sb + OFF_OA + (lane >> 4) * 2048 + (32 * w + 2 * (lane & 15) + par) * 16;
#pragma unroll
  for (int j = 0; j < 5; j++) stsm4(oa + 4096 * j, ov + 4 * j);
  TSIF(par == 0 && w == 0, 120);
  fence_async_smem();
  TSIF(par == 0 && w == 0, 121);
  __syncwarp();
  if (lane == 0) mbar_arrive(sb + OFF_BAR + 8 * B_ATTN);
  TSM(w == 0 || w == 2, 122 + par + (w == 2 ? 3 : 0));
}

struct Maps {
  CUtensorMap x, wm, wt, k, v, y, wo, qm, qt, om, ot, yl, ol;
};

__device__ __forceinline__ void load_stage(uint32_t sb, int kb, int b, const Maps& m) {
  const uint32_t st = sb + (kb & 3) * STAGE_BYTES, bar = sb + OFF_BAR + 8 * (B_FULL1 + (kb & 3));
  const int r = b >> 3, hg = b & 7, slab = kb - KV_KB;
  const bool kv = slab >= 0 && slab < 5;
  const uint32_t kbar = sb + OFF_BAR + 8 * (B_KV + slab), dst = sb + OFF_KVS + slab * KVS_BYTES;
  mbar_expect_tx(bar, STAGE_BYTES);
  if (kv) mbar_expect_tx(kbar, KVS_BYTES);
  tma_3d(st, &m.x, 64 * kb, 64 * r, 0, bar);
  tma_3d(st + ST_W, &m.wm, 80 * hg + (tail_first(hg) ? 16 : 0), 64 * kb, 0, bar);
  tma_3d(st + ST_WT, &m.wt, 80 * hg + (tail_first(hg) ? 0 : 64), 64 * kb, 0, bar);
  if (kv) tma_3d(dst, &m.k, 0, 32 * (b >> 1) - 3, 2 * slab + (b & 1), kbar);
  if (kv) tma_3d(dst + KVS_V, &m.v, 0, 32 * (b >> 1), 2 * slab + (b & 1), kbar);
}

__global__ void __launch_bounds__(NTHR, 1) fused_kernel(const __grid_constant__ Maps m, const Params p) {
  extern __shared__ __align__(1024) uint8_t smem[];
  const uint32_t sb = (uint32_t)__cvta_generic_to_shared(smem);
  const uint32_t bars = sb + OFF_BAR;
  const int tid = threadIdx.x, lane = tid & 31;
  int b = blockIdx.x;
  b = (((b & 63) >> 3) * 2 + (b & 1)) * 8 + (((b < 64 ? 0x6521 : 0x7430) >> (4 * ((b >> 1) & 3))) & 7);
  const int r = b >> 3, hg = b & 7;

  if (tid == T_ISSUE) {
    TSM(true, 0);
    mbar_init(bars + 8 * B_F0, 1);
    fence_async_smem();
    mbar_expect_tx(bars + 8 * B_F0, ST_WT);
    tma_3d(sb, &m.x, 0, 64 * r, 0, bars + 8 * B_F0);
    tma_3d(sb + ST_W, &m.wm, 80 * hg + (tail_first(hg) ? 16 : 0), 0, 0, bars + 8 * B_F0);
#pragma unroll
    for (int i = 0; i < 4; i++) mbar_init(bars + 8 * (B_FULL1 + i), 1);
    fence_async_smem();
    mbar_expect_tx(bars + 8 * B_FULL1, STAGE_BYTES - ST_WT);
    tma_3d(sb + ST_WT, &m.wt, 80 * hg + (tail_first(hg) ? 0 : 64), 0, 0, bars + 8 * B_FULL1);
    load_stage(sb, 1, b, m);
  } else if (tid == T_INIT) {
#pragma unroll
    for (int i = 0; i < B_F0; i++) mbar_init(bars + 8 * i, i < B_GATE ? 8 : i < B_CVD ? 4 : i == B_CVD ? 20 : 1);
    fence_async_smem();
  }
  const int warp = __shfl_sync(0xffffffffu, tid >> 5, 0), wg = warp >> 2, w = warp & 3;
  __syncthreads();

  if (wg == 3) {
    asm volatile("setmaxnreg.dec.sync.aligned.u32 56;");
    if (w == 0) {
      if (lane == 0) {
#pragma unroll 1
        for (int kb = 2; kb < 10; kb++) {
          if (kb >= 4) mbar_wait(bars + 8 * (kb == 7 ? B_E3 : B_EMPTY1 + (kb & 3)), (kb >> 3) & 1);
          TSIF(kb >= 4, 44 + kb);
          load_stage(sb, kb, b, m);
          TSIF(kb == 3, 60);
          if (kb == TRIG_KB) mbar_arrive(bars + 8 * B_LAST);
        }
        mbar_wait(bars + 8 * B_P1, 0);
        mbar_wait(bars + 8 * B_KVD, 0);
        mbar_wait(bars + 8 * Q_TRIG, 0);
        mbar_expect_tx(bars + 8 * B_QF, O_BYTES);
        tma_2d(sb + OFF_QS, &m.qm, 80 * hg, 128 * r, bars + 8 * B_QF);
        tma_2d(sb + OFF_QT, &m.qt, 80 * hg + 64, 128 * r, bars + 8 * B_QF);
        mbar_wait(bars + 8 * B_WOP, 0);
        mbar_wait(bars + 8 * WL_TRIG, 0);
        mbar_wait(bars + 8 * B_EPOCH, 0);
        flag_wait(g_cnt + C_W + 32 * hg, (lds32(sb + OFF_EPOCH) + 1) * 16);
        TS(30);
#pragma unroll 1
        for (int j = 0; j < 8; j++) {
          if (j >= 6) mbar_wait(bars + 8 * (B_EMPTY2 + j - 6), 0);
          if (j == 4) mbar_wait(bars + 8 * (RB32 & 2 ? B_ORB : B_ATTN), 0);
          TSIF(j >= 6, 100 + j);
          mbar_expect_tx(bars + 8 * (B_FULL2 + j), j == 0 ? WO_BYTES : j == 5 ? O_BYTES + WO_BYTES + 512 : O_BYTES + WO_BYTES);
          bulk_load(sb + off_w(j), g_WO + (hg * 8 + step_src(hg, j)) * 800, WO_BYTES, bars + 8 * (B_FULL2 + j));
        }
      }
    } else if (w == 1) {
      unsigned epoch = 0;
      if (lane == 0) {
        epoch = atomicAdd(g_cnt + C_LAUNCH, 1u) / NCTA;
        asm volatile("st.shared.u32 [%0], %1;" ::"r"(sb + OFF_EPOCH), "r"(epoch) : "memory");
        mbar_arrive(bars + 8 * B_EPOCH);
        mbar_wait(bars + 8 * B_KVD, 0);
        mbar_expect_tx(bars + 8 * B_HB, 5 * 4096);
#pragma unroll 1
        for (int c = 0; c < 5; c++) {
          if (c == 3) mbar_wait(bars + 8 * B_S3, 0);
          bulk_load(sb + off_ch(c) + U_BYTES, p.ssm_k + (5 * b + c) * SEQ, 4096, bars + 8 * B_HB);
        }
#pragma unroll
        for (int c = 0; c < 4; c++) mbar_expect_tx(bars + 8 * (B_U + c), c < 3 ? U_BYTES : 2 * U_BYTES);
        const uint4* usrc = g_U + 5 * b * U_PITCH;
        mbar_wait(bars + 8 * B_USIG, 0);
        flag_wait(g_cnt + C_PREP + 32 * (b & 15), (epoch + 1) * NCTA);
        TS(23);
#pragma unroll
        for (int c = 0; c < 5; c++) {
          if (c == 3) mbar_wait(bars + 8 * (B_U + 2), 0);
          bulk_load(sb + off_ch(c), usrc + c * U_PITCH, U_BYTES, bars + 8 * (B_U + (c < 3 ? c : 3)));
          TSIF(c == 0 || c == 4, 116 + (c >> 2));
        }
      }
      epoch = __shfl_sync(0xffffffffu, epoch, 0);
      if (lane < 8) {
        const int src = (b & ~7) | step_src(hg, lane);
        mbar_wait(bars + 8 * B_ATTN, 0);
        TS(20);
        bool seen = false;
#pragma unroll 1
        for (int spins = 0; spins < SPIN_LIMIT; spins++) {
          const bool now = !seen && (int)(flag_read(g_cnt + C_O + 32 * src) - (epoch + 1)) >= 0;
          if (now && lane >= 1 && lane < 4) bulk_load(sb + off_o(lane), g_O + src * 1280, O_BYTES, bars + 8 * (B_FULL2 + lane));
          seen = seen || now;
          if (__all_sync(0xff, seen)) break;
        }
        TS(21);
        if (lane == 5) bulk_load(sb + OFF_GATE, g_gate + 128 * r, 512, bars + 8 * (B_FULL2 + 5));
#pragma unroll 1
        for (int j = 4; j < 8; j++) {
          if (lane == j) {
            mbar_wait(bars + 8 * (j == 4 ? B_C34 : j == 5 ? B_YRB : B_EMPTY2 + j - 6), 0);
            bulk_load(sb + off_o(j), g_O + src * 1280, j == 5 ? 16384 : O_BYTES, bars + 8 * (B_FULL2 + j));
            if (j == 5) bulk_load(sb + OFF_CH0 + O_BYTES, g_O + src * 1280 + 1024, 4096, bars + 8 * (B_FULL2 + j));
          }
          __syncwarp(0xff);
        }
        TS(22);
      }
    } else if (w == 2) {
      mbar_wait(bars + 8 * B_PREP, 0);
      flag_signal(g_cnt + C_PREP, 16, lane);
      TS(25);
      if (lane == 0) {
        mbar_arrive(bars + 8 * B_USIG);
        mbar_expect_tx(bars + 8 * B_ORB, (RB32 & 2 ? O_BYTES / 4 : O_BYTES) + 64);
        mbar_wait(bars + 8 * B_GATE, 0);
        publish(g_gate + 16 * b, sb + OFF_GATE + 64 * hg, 64, bars + 8 * B_ORB);
        mbar_wait(bars + 8 * B_ATTN, 0);
        if (RB32 & 2) {
          bulk_store(g_O + b * 1280, sb + OFF_OA, O_BYTES);
          bulk_wait_read();
          tma_2d(sb + OFF_KVX + 10240, &m.ol, 48, b * 160, bars + 8 * B_ORB);
        } else {
          publish(g_O + b * 1280, sb + OFF_OA, O_BYTES, bars + 8 * B_ORB);
        }
        TS(74);
        mbar_wait(bars + 8 * B_ORB, 0);
        flag_bump(g_cnt + C_O + 32 * b);
        TS(26);
        mbar_arrive(bars + 8 * B_OSIG);
      }
    } else {
      if (lane == 0) {
        uint4* dst = g_WO + (hg * 8 + (r >> 1)) * 800 + (r & 1) * 80;
        mbar_wait(bars + 8 * B_S3, 0);
        asm volatile("cp.async.bulk.prefetch.L2.global [%0], 6400;" ::"l"(p.wo + b * 3200) : "memory");
        mbar_wait(bars + 8 * B_P1, 0);
        mbar_wait(bars + 8 * WB_TRIG, 0);
        mbar_expect_tx(bars + 8 * B_WST, WO_BYTES / 2);
        tma_3d(sb + OFF_WA, &m.wo, 0, 40 * r, 5 * hg, bars + 8 * B_WST);
        mbar_wait(bars + 8 * B_WST, 0);
#pragma unroll 1
        for (int n = 0; n < 5; n++) bulk_store(dst + 160 * n, sb + OFF_WA + 1280 * n, 1280);
        bulk_wait_read();
        mbar_expect_tx(bars + 8 * B_WST, WO_BYTES / 2);
#pragma unroll 1
        for (int n = 0; n < 5; n++) bulk_load(sb + OFF_WA + 1280 * n, dst + 160 * n, 1280, bars + 8 * B_WST);
        mbar_wait(bars + 8 * B_WST, 1);
        flag_bump(g_cnt + C_W + 32 * hg);
        mbar_arrive(bars + 8 * B_WOP);
        TS(71);
        mbar_expect_tx(bars + 8 * B_C34, 3 * (RB32 & 1 ? 1024 : U_BYTES));
        mbar_expect_tx(bars + 8 * B_YRB, 2 * (RB32 & 1 ? 1024 : U_BYTES));
#pragma unroll 1
        for (int c = 0; c < 5; c++) {
          mbar_wait(bars + 8 * (B_YST + c), 0);
          if (RB32 & 1) {
            bulk_store(g_U + (5 * b + c) * U_PITCH, sb + off_ch(c), U_BYTES);
            bulk_wait_read();
            tma_2d(sb + off_ch(c), &m.yl, 48, (5 * b + c) * (U_PITCH / 8), bars + 8 * (c < 3 ? B_C34 : B_YRB));
          } else {
            publish(g_U + (5 * b + c) * U_PITCH, sb + off_ch(c), U_BYTES, bars + 8 * (c < 3 ? B_C34 : B_YRB));
          }
        }
        TS(75);
        mbar_wait(bars + 8 * B_C34, 0);
        mbar_wait(bars + 8 * B_YRB, 0);
        flag_bump(g_cnt + C_Y + 32 * (b >> 4));
        TS(27);
        mbar_arrive(bars + 8 * B_YSIG);
        mbar_expect_tx(bars + 8 * B_YFULL, 20480);
        flag_wait(g_cnt + C_Y + 32 * hg, (lds32(sb + OFF_EPOCH) + 1) * 16);
        TS(24);
        mbar_wait(bars + 8 * (B_EMPTY2 + 2), 0);
        tma_2d(sb + OFF_YT, &m.y, 128 * r, 80 * hg, bars + 8 * B_YFULL);
        tma_2d(sb + OFF_YT + 10240, &m.y, 128 * r + 64, 80 * hg, bars + 8 * B_YFULL);
      }
    }
  } else {
    asm volatile("setmaxnreg.inc.sync.aligned.u32 152;");
    if (wg < 2) {
      float acc[120];
#pragma unroll
      for (int i = 0; i < 120; i++) acc[i] = 0.f;
      const uint32_t da = desc_lo(sb + wg * 8192, 16), db = desc_lo(sb + ST_W, 8192), dc = desc_lo(sb + ST_WT, 2048);
      mbar_wait(bars + 8 * B_F0, 0);
      TSIF(w == 0 && wg == 0, 1);
      wg_fence();
#pragma unroll
      for (int k = 0; k < 4; k++) WgSST<192>::mma<HI_SW128, HI_SW128>(acc, da + 2 * k, db + 128 * k, 1);
      wg_commit();
      mbar_wait(bars + 8 * B_FULL1, 0);
      wg_fence();
#pragma unroll
      for (int k = 0; k < 4; k++) WgSST<48>::mma<HI_SW128, HI_SW32>(acc + 96, da + 2 * k, dc + 32 * k, 1);
      wg_commit();
#pragma unroll 1
      for (int kb = 1; kb < 10; kb++) {
        mbar_wait(bars + 8 * (B_FULL1 + (kb & 3)), (kb >> 2) & 1);
        const uint32_t so = (kb & 3) * (STAGE_BYTES >> 4);
        wg_fence();
#pragma unroll
        for (int k = 0; k < 4; k++) {
          WgSST<192>::mma<HI_SW128, HI_SW128>(acc, da + so + 2 * k, db + so + 128 * k, 1);
          WgSST<48>::mma<HI_SW128, HI_SW32>(acc + 96, da + so + 2 * k, dc + so + 32 * k, 1);
        }
        wg_commit();
        wg_wait<1>();
        if (lane == 0) mbar_arrive(bars + 8 * (kb == 4 ? B_E3 : B_EMPTY1 + ((kb - 1) & 3)));
      }
      mbar_wait(bars + 8 * B_EPOCH, 0);
      const uint32_t tag = lds32(sb + OFF_EPOCH) + 1;
      mbar_wait(bars + 8 * B_S3, 0);
      wg_wait<0>();
      pin<120>(acc);
      if (lane == 0) mbar_arrive(bars + 8 * B_P1);
      TSM(w == 0, 3 + wg);
      attention(acc, sb, b, wg, w, lane, tag);
    } else {
      const int tw = tid & 127, chl = 64 * (b & 1) + 8 * w + (lane >> 2);
      uint4* up = g_U + chl * U_PITCH + ((4 * (b >> 1) + (lane & 3)) ^ ((b >> 2) & 1));
      uint2 sw[10];
      uint32_t dv = 0;
      if (lane < 5) dv = __ldg(reinterpret_cast<const unsigned short*>(p.ssm_D) + 5 * b + lane);
#pragma unroll
      for (int i = 0; i < 10; i++) sw[i] = ldg64(reinterpret_cast<const uint2*>(p.shift_k) + chl + 128 * (i >> 1) + 32 * (i & 1));
      uint32_t tab[12];
      uint32_t tt[2];
      fft_tables(tab, tw);
      fft_twiddles(tt, tw);
      uint4 res[10];
#pragma unroll
      for (int i = 0; i < 10; i++) res[i] = make_uint4(0, 0, 0, 0);
#pragma unroll 1
      for (int slab = 0; slab < 5; slab++) {
#pragma unroll
        for (int i = 0; i < 8; i++) res[i] = res[i + 2];
        prep_slab(res + 8, sw, sb, slab, w, lane);
        TSIF(w == 0, 99 + 4 * slab);
#pragma unroll
        for (int i = 0; i < 8; i++) sw[i] = sw[i + 2];
      }
      TSIF(w == 0, 28);
      __syncwarp();
      if (lane == 0) mbar_arrive(bars + 8 * B_KVD + ((res[8].x ^ res[9].x) & p.zero));
      mbar_wait(bars + 8 * B_KVD, 0);
      fft_tables_store(tab, sb, tw);
      mbar_wait(bars + 8 * B_LAST, 0);
#pragma unroll
      for (int i = 0; i < 10; i++) up[(128 * (i >> 1) + 32 * (i & 1)) * U_PITCH] = res[i];
      __syncwarp();
      if (lane == 0) mbar_arrive(bars + 8 * B_PREP);
      TSIF(w == 0, 5);
      mbar_wait(bars + 8 * B_LAST, 0);
      prep_gate(p, sb, b, w, lane);
      __syncwarp();
      if (lane == 0) mbar_arrive(bars + 8 * B_GATE);
      TSIF(w == 0, 72);
      mbar_wait(bars + 8 * B_HB, 0);
      TSIF(w == 0, 2);
      const uint32_t ha = sb + U_BYTES + ((tw >> 3) * 16 + 8 + (tw & 7)) * 16;
      uint4 hv[5];
#pragma unroll
      for (int c = 0; c < 5; c++) hv[c] = lds128(ha + off_ch(c));
      __syncwarp();
#pragma unroll
      for (int c = 0; c < 5; c++) sts128((ha ^ 16) + off_ch(c), hv[c].x, hv[c].y, hv[c].z, hv[c].w);
      asm volatile("st.shared.v2.u32 [%0], {%1, %2};" ::"r"(sb + OFF_TT + 8 * tw), "r"(tt[0]), "r"(tt[1]) : "memory");
      if (tw < 5) asm volatile("st.shared.f32 [%0], %1;" ::"r"(sb + OFF_D + 4 * tw), "f"(bf_lo(dv) * 0.125f) : "memory");
      fence_async_smem();
      __syncwarp();
      if (lane == 0) mbar_arrive(bars + 8 * B_HA);
      TSIF(w == 0, 6);
    }

    FftConst fc;
    TSM(w == 0 && wg == 0, 104);
    mbar_wait(bars + 8 * B_HA, 0);
    fft_matrices(fc, sb, w, lane);
    TSM(w == 0 && wg == 0, 105);
    TSM(w == 0 && wg == 2, 124);
#pragma unroll 1
    for (uint32_t tasks = wg == 0 ? TASK0 : wg == 1 ? TASK1 : TASK2; tasks; tasks >>= 4) {
      const int c = (tasks & 7) - 1;
      conv_channel(fc, sb, c, wg, w, lane);
      if (lane == 0) mbar_arrive(bars + 8 * (B_YST + c));
      TSM(w == 0, 10 + c);
    }

    if (wg < 2) {
      const int g = lane >> 2;
      float acc[40];
#pragma unroll
      for (int i = 0; i < 40; i++) acc[i] = 0.f;
      const uint32_t da = desc_lo(sb + wg * 1024, 2048), db = desc_lo(sb, 2560);
      mbar_wait(bars + 8 * B_ORB, 0);
      mbar_wait(bars + 8 * B_FULL2, 0);
      mbar_wait(bars + 8 * B_CVD, 0);
      TSM(w == 0, 15 + wg);
#pragma unroll 1
      for (int j = 0; j < 8; j++) {
        mbar_wait(bars + 8 * (B_FULL2 + j), 0);
        TSM(w == 0 && wg == 0, 44 + (j < 4 ? j : j + 6));
        const uint32_t oa = da + (off_o(j) >> 4), ob = db + (off_w(j) >> 4);
        wg_fence();
#pragma unroll
        for (int k = 0; k < 5; k++)
          WgSST<80>::mma<HI_NONE, HI_SW32>(acc, k == 4 && j == 5 ? da + ((OFF_CH0 + O_BYTES) >> 4) : oa + 256 * k, ob + 32 * k, 1);
        wg_commit();
        wg_wait<1>();
        if (j >= 1 && j <= 3 && lane == 0) mbar_arrive(bars + 8 * (B_EMPTY2 + j - 1));
      }
      TSIF(w == 0 && wg == 0, 113);
      const int tr = 64 * wg + 16 * w + (lane & 15);
      const uint32_t fm = sb + OFF_QS + tr * 128, fx = (lane >> 4) ^ (tr & 7);
      const uint32_t ft = sb + OFF_QT + tr * 32 + (((lane >> 4) ^ (tr >> 2)) & 1) * 16;
      const float g0 = __uint_as_float(lds32(sb + OFF_GATE + (64 * wg + 16 * w + g) * 4));
      const float g1 = __uint_as_float(lds32(sb + OFF_GATE + (64 * wg + 16 * w + 8 + g) * 4));
      const uint32_t ga = pack2(g0, g0), gb = pack2(g1, g1);
      const uint32_t na = pack2(1.f - g0, 1.f - g0), nb = pack2(1.f - g1, 1.f - g1);

      uint32_t qf[20];
      mbar_wait(bars + 8 * B_QF, 0);
      TSM(w == 0 && wg == 0, 99);
#pragma unroll
      for (int j = 0; j < 5; j++) ldsm4(qf + 4 * j, j < 4 ? fm + ((fx ^ (2 * j)) << 4) : ft);
#pragma unroll
      for (int i = 0; i < 20; i++) {
        qf[i] = bmul((i & 1) ? gb : ga, qf[i]);
        asm volatile("" : "+r"(qf[i]));
      }

      wg_wait<0>();
      pin<40>(acc);
      TSM(w == 0, 17 + wg);
      uint32_t pb[20];
#pragma unroll
      for (int j = 0; j < 10; j++) {
        pb[2 * j] = bmul(na, pack2(acc[4 * j], acc[4 * j + 1]));
        pb[2 * j + 1] = bmul(nb, pack2(acc[4 * j + 2], acc[4 * j + 3]));
        asm volatile("" : "+r"(pb[2 * j]), "+r"(pb[2 * j + 1]));
      }
      const uint32_t ya = sb + OFF_YT + wg * 10240 + ((lane >> 4) * 8 + (lane & 7)) * 128 +
                          (((2 * w + (((lane >> 3) & 1) ^ wg)) ^ (lane & 7)) << 4);
      mbar_wait(bars + 8 * B_YFULL, 0);
      TSM(w == 0 && wg == 0, 19);
#pragma unroll
      for (int j = 0; j < 5; j++) {
        uint32_t y[4];
        ldsm4t(y, ya + 2048 * j);
#pragma unroll
        for (int i = 0; i < 4; i++)
          qf[4 * j + i] = bfma(qf[4 * j + i], y[i], pb[4 * j + i]);
      }
#pragma unroll
      for (int j = 0; j < 5; j++) stsm4(j < 4 ? fm + ((fx ^ (2 * j)) << 4) : ft, qf + 4 * j);
      fence_async_smem();
      __syncwarp();
      if (lane == 0) {
        const int row = 64 * wg + 16 * w;
        asm volatile("cp.async.bulk.tensor.2d.global.shared::cta.bulk_group [%0, {%2, %3}], [%1];"
                     ::"l"(&m.om), "r"(sb + OFF_QS + row * 128), "r"(80 * hg), "r"(128 * r + row) : "memory");
        asm volatile("cp.async.bulk.tensor.2d.global.shared::cta.bulk_group [%0, {%2, %3}], [%1];"
                     ::"l"(&m.ot), "r"(sb + OFF_QT + row * 32), "r"(80 * hg + 64), "r"(128 * r + row) : "memory");
        asm volatile("cp.async.bulk.commit_group;\ncp.async.bulk.wait_group.read 0;" ::: "memory");
      }
      TSM(w == 0 || w == 3, 40 + 2 * wg + (w & 1));
    }
  }
}

typedef CUresult (*EncodeFn)(CUtensorMap*, CUtensorMapDataType, cuuint32_t, void*, const cuuint64_t*, const cuuint64_t*,
                             const cuuint32_t*, const cuuint32_t*, CUtensorMapInterleave, CUtensorMapSwizzle,
                             CUtensorMapL2promotion, CUtensorMapFloatOOBfill);

void encode(EncodeFn fn, CUtensorMap* tm, const void* base, int rank, const cuuint64_t* dims, const cuuint64_t* strides,
            const cuuint32_t* box, CUtensorMapSwizzle swz) {
  const cuuint32_t ones[3] = {1, 1, 1};
  fn(tm, CU_TENSOR_MAP_DATA_TYPE_BFLOAT16, rank, const_cast<void*>(base), dims, strides, box, ones,
     CU_TENSOR_MAP_INTERLEAVE_NONE, swz, CU_TENSOR_MAP_L2_PROMOTION_L2_128B, CU_TENSOR_MAP_FLOAT_OOB_FILL_NONE);
}

}

extern "C" void kernel_launch(void* const* d_in, const int* in_sizes, int n_in, void* d_out, int out_size) {
  (void)in_sizes; (void)n_in; (void)out_size;
  Params p;
  p.q = (const __nv_bfloat16*)d_in[0];
  p.k = (const __nv_bfloat16*)d_in[1];
  p.v = (const __nv_bfloat16*)d_in[2];
  p.shift_k = (const __nv_bfloat16*)d_in[3];
  p.ssm_k = (const __nv_bfloat16*)d_in[4];
  p.ssm_D = (const __nv_bfloat16*)d_in[5];
  p.wqkv = (const __nv_bfloat16*)d_in[7];
  p.wo = (const __nv_bfloat16*)d_in[8];
  p.gate_w = (const __nv_bfloat16*)d_in[9];
  p.out = (__nv_bfloat16*)d_out;
  p.zero = 0;

  static EncodeFn fn = nullptr;
  static void *yaddr = nullptr, *oaddr = nullptr;
  if (!fn) {
    cudaDriverEntryPointQueryResult qr;
    void* f = nullptr;
    cudaGetDriverEntryPoint("cuTensorMapEncodeTiled", &f, cudaEnableDefault, &qr);
    fn = (EncodeFn)f;
    cudaGetSymbolAddress(&yaddr, g_U);
    cudaGetSymbolAddress(&oaddr, g_O);
    cudaFuncSetAttribute(fused_kernel, cudaFuncAttributeMaxDynamicSharedMemorySize, SMEM_BYTES);
  }
  Maps m;
  {
    const cuuint64_t dims[3] = {640, 1024, 2}, st[2] = {2560, 1280};
    const cuuint32_t box[3] = {64, 64, 2};
    encode(fn, &m.x, p.q, 3, dims, st, box, CU_TENSOR_MAP_SWIZZLE_128B);
  }
  {
    const cuuint64_t dims[3] = {640, 640, 3}, st[2] = {3840, 1280};
    const cuuint32_t box[3] = {64, 64, 3}, boxt[3] = {16, 64, 3};
    encode(fn, &m.wm, p.wqkv, 3, dims, st, box, CU_TENSOR_MAP_SWIZZLE_128B);
    encode(fn, &m.wt, p.wqkv, 3, dims, st, boxt, CU_TENSOR_MAP_SWIZZLE_32B);
  }
  {
    const cuuint64_t dims[3] = {64, 2048, 10}, st[2] = {1280, 128};
    const cuuint32_t boxk[3] = {64, 35, 1}, boxv[3] = {64, 32, 1};
    encode(fn, &m.k, p.k, 3, dims, st, boxk, CU_TENSOR_MAP_SWIZZLE_128B);
    encode(fn, &m.v, p.v, 3, dims, st, boxv, CU_TENSOR_MAP_SWIZZLE_128B);
  }
  {
    const cuuint64_t dims[3] = {16, 640, 40}, st[2] = {1280, 32};
    const cuuint32_t box[3] = {16, 40, 5};
    encode(fn, &m.wo, p.wo, 3, dims, st, box, CU_TENSOR_MAP_SWIZZLE_32B);
  }
  {
    const cuuint64_t dims[2] = {2048, 640}, st[1] = {U_PITCH * 16};
    const cuuint32_t box[2] = {64, 80};
    encode(fn, &m.y, yaddr, 2, dims, st, box, CU_TENSOR_MAP_SWIZZLE_128B);
    const cuuint64_t dl[2] = {64, DIM * U_PITCH / 8}, dol[2] = {64, NCTA * 160}, sl[1] = {128};
    const cuuint32_t bl[2] = {16, 32}, bol[2] = {16, 160};
    encode(fn, &m.yl, yaddr, 2, dl, sl, bl, CU_TENSOR_MAP_SWIZZLE_NONE);
    encode(fn, &m.ol, oaddr, 2, dol, sl, bol, CU_TENSOR_MAP_SWIZZLE_NONE);
  }
  {
    const cuuint64_t dims[2] = {640, 2048}, st[1] = {1280};
    const cuuint32_t bqm[2] = {64, 128}, bqt[2] = {16, 128}, bom[2] = {64, 16}, bot[2] = {16, 16};
    encode(fn, &m.qm, p.q, 2, dims, st, bqm, CU_TENSOR_MAP_SWIZZLE_128B);
    encode(fn, &m.qt, p.q, 2, dims, st, bqt, CU_TENSOR_MAP_SWIZZLE_32B);
    encode(fn, &m.om, p.out, 2, dims, st, bom, CU_TENSOR_MAP_SWIZZLE_128B);
    encode(fn, &m.ot, p.out, 2, dims, st, bot, CU_TENSOR_MAP_SWIZZLE_32B);
  }
  fused_kernel<<<NCTA, NTHR, SMEM_BYTES>>>(m, p);
}
```

```cpp
#include <cuda.h>
#include <cuda_bf16.h>
#include <cuda_runtime.h>
#include <stdint.h>

namespace {

constexpr int SEQ = 2048, DIM = 640, NCTA = 128, NTHR = 512;

#define TRIG_KB 9
#define KV_KB 2
#define DEV_EXIT 0
#define FENCE_LO 0
#define FENCE_HI 0
#define WB_TRIG B_USIG
#define T_ISSUE 256
#define RB32 3
#define WO_SKIP 1
#define T_INIT 448
#define TASK0 0x3
#define TASK1 0x52
#define TASK2 0x41
#define WL_TRIG B_WOP

constexpr uint32_t STAGE_BYTES = 47104, ST_W = 16384, ST_WT = 40960;
constexpr uint32_t O_BYTES = 20480, WO_BYTES = 12800;
constexpr uint32_t OFF_OA = 0;
constexpr uint32_t OFF_QS = 3 * O_BYTES, OFF_QT = OFF_QS + 16384;
constexpr uint32_t OFF_WC = 81920;
constexpr uint32_t OFF_WA = 94720;
constexpr uint32_t OFF_GATE = 145920;
constexpr uint32_t OFF_TT = 146432;
constexpr uint32_t OFF_KVX = 148480;
constexpr uint32_t OFF_CH3 = 163840;
constexpr uint32_t CH_BYTES = 12288, U_BYTES = 4096;
constexpr uint32_t OFF_FT = 225280, OFF_GT = 229376;
constexpr uint32_t OFF_CH0 = 188416;
constexpr uint32_t OFF_KVS = OFF_CH0, KVS_V = 4480, KVS_BYTES = 8576;
constexpr uint32_t OFF_YT = 163840;
constexpr uint32_t OFF_BAR = 231936;
constexpr uint32_t SMEM_BYTES = OFF_BAR + 512;

enum : uint32_t {
  B_EMPTY1 = 0, B_S3 = 3, B_E3 = 4, B_EMPTY2 = 5, B_ATTN = 9, B_P1 = 10,
  B_GATE = 11, B_HA = 12, B_KVD = 13, B_PREP = 14, B_YST = 15,
  B_CVD = 20,
  B_FULL2 = 21, B_U = 29, B_KV = 33, B_HB = 38, B_C34 = 39, B_YRB = 40, B_YFULL = 41, B_EPOCH = 42, B_LAST = 43, B_OSIG = 44,
  B_WOP = 45, B_USIG = 46, B_WST = 47, B_QF = 48, B_ORB = 49, B_YSIG = 50,
  B_F0 = 51, B_FULL1 = 52
};
constexpr uint32_t OFF_EPOCH = OFF_BAR + 8 * 58, OFF_D = OFF_BAR + 8 * 60;
__device__ __forceinline__ uint32_t off_o(int j) { return j < 4 ? OFF_OA + j * O_BYTES : j < 6 ? OFF_CH0 + (j - 4) * O_BYTES : OFF_OA + (j - 6) * O_BYTES; }
__device__ __forceinline__ uint32_t off_w(int j) { return j < 4 ? OFF_WA + j * WO_BYTES : j == 4 ? OFF_KVX : j == 5 ? OFF_WC : OFF_WA + (j - 6) * WO_BYTES; }
__device__ __forceinline__ int step_src(int hg, int j) { return j == 0 ? hg : j <= hg ? j - 1 : j; }
__device__ __forceinline__ bool tail_first(int hg) { return (hg & 3) == 3; }
__device__ __forceinline__ uint32_t off_ch(int c) { return (c < 3 ? OFF_CH0 : OFF_CH3 - 3 * CH_BYTES) + c * CH_BYTES; }

#define U_PITCH 264
__device__ __align__(1024) uint4 g_U[DIM * U_PITCH];
__device__ __align__(128) uint4 g_O[NCTA * 1280];
__device__ uint4 g_WO[64 * 800];
__device__ uint4 g_halo[NCTA * 2 * 7 * 32];
__device__ __align__(128) float g_gate[SEQ];
__device__ unsigned g_cnt[32 * (1 + 2 * 16 + 8 + NCTA)];
constexpr int C_LAUNCH = 0, C_PREP = 32, C_Y = 32 * 17, C_W = 32 * 33, C_O = 32 * 41;

#define TSM(cond, slot) do { } while (0)
#define TSIF(cond, slot) do { if (__LINE__ >= FENCE_LO && __LINE__ < FENCE_HI) sched_fence(); } while (0)
__device__ __forceinline__ void sched_fence() {
  asm volatile("{\n.reg .pred p;\n.reg .u32 c;\nmov.u32 c, %%clock;\nsetp.eq.u32 p, c, 0;\n@p st.shared.u32 [%0], c;\n}"
               ::"r"(1024 + OFF_EPOCH + 4) : "memory");
}
#define TS(slot) TSIF(true, slot)

struct Params {
  const __nv_bfloat16 *q, *k, *v, *shift_k, *ssm_k, *ssm_D, *wqkv, *wo, *gate_w;
  __nv_bfloat16* out;
  uint32_t zero;
};

constexpr int SPIN_LIMIT = 1 << 17;

__device__ __forceinline__ void mbar_init(uint32_t bar, uint32_t count) {
  asm volatile("mbarrier.init.shared::cta.b64 [%0], %1;" ::"r"(bar), "r"(count) : "memory");
}
__device__ __forceinline__ void mbar_expect_tx(uint32_t bar, uint32_t bytes) {
  asm volatile("mbarrier.arrive.expect_tx.shared::cta.b64 _, [%0], %1;" ::"r"(bar), "r"(bytes) : "memory");
}
__device__ __forceinline__ void mbar_arrive(uint32_t bar) {
  asm volatile("mbarrier.arrive.shared::cta.b64 _, [%0];" ::"r"(bar) : "memory");
}
__device__ __forceinline__ void mbar_wait(uint32_t bar, uint32_t parity) {
  uint32_t ok;
  int spins = 0;
  do {
      asm volatile("{\n.reg .pred p;\nmbarrier.try_wait.parity.shared::cta.b64 p, [%1], %2;\nselp.b32 %0, 1, 0, p;\n}"
                   : "=r"(ok) : "r"(bar), "r"(parity) : "memory");
    if (++spins > SPIN_LIMIT) break;
  } while (!ok);
}
__device__ __forceinline__ unsigned flag_read(const unsigned* p) {
  unsigned v;
  asm volatile("ld.relaxed.gpu.global.u32 %0, [%1];" : "=r"(v) : "l"(p) : "memory");
  return v;
}
__device__ __forceinline__ void flag_poll(const unsigned* p, unsigned target) {
  unsigned v;
  int spins = 0;
  do {
    asm volatile("ld.relaxed.gpu.global.u32 %0, [%1];" : "=r"(v) : "l"(p) : "memory");
    if (++spins > SPIN_LIMIT) break;
  } while ((int)(v - target) < 0);
}
__device__ __forceinline__ void flag_wait(const unsigned* p, unsigned target) {
  flag_poll(p, target);
}
__device__ __forceinline__ void flag_signal(unsigned* p, int n, int lane) {
  if (lane == 0) asm volatile("fence.release.gpu;" ::: "memory");
  __syncwarp();
  if (lane < n) asm volatile("red.relaxed.gpu.global.add.u32 [%0], 1;" ::"l"(p + 32 * lane) : "memory");
}
__device__ __forceinline__ void flag_bump(unsigned* p) {
  asm volatile("red.relaxed.gpu.global.add.u32 [%0], 1;" ::"l"(p) : "memory");
}
__device__ __forceinline__ void fence_async_smem() { asm volatile("fence.proxy.async.shared::cta;" ::: "memory"); }
__device__ __forceinline__ void wg_sync(int id) { asm volatile("bar.sync %0, 128;" ::"r"(id) : "memory"); }

__device__ __forceinline__ void tma_2d(uint32_t dst, const CUtensorMap* tm, int c0, int c1, uint32_t bar) {
  asm volatile("cp.async.bulk.tensor.2d.shared::cluster.global.mbarrier::complete_tx::bytes [%0], [%1, {%3, %4}], [%2];"
               ::"r"(dst), "l"(tm), "r"(bar), "r"(c0), "r"(c1) : "memory");
}
__device__ __forceinline__ void tma_3d(uint32_t dst, const CUtensorMap* tm, int c0, int c1, int c2, uint32_t bar) {
  asm volatile("cp.async.bulk.tensor.3d.shared::cluster.global.mbarrier::complete_tx::bytes [%0], [%1, {%3, %4, %5}], [%2];"
               ::"r"(dst), "l"(tm), "r"(bar), "r"(c0), "r"(c1), "r"(c2) : "memory");
}
__device__ __forceinline__ void bulk_load(uint32_t dst, const void* src, uint32_t bytes, uint32_t bar) {
  asm volatile("cp.async.bulk.shared::cluster.global.mbarrier::complete_tx::bytes [%0], [%1], %2, [%3];"
               ::"r"(dst), "l"(src), "r"(bytes), "r"(bar) : "memory");
}
__device__ __forceinline__ void bulk_store(void* dst, uint32_t src, uint32_t bytes) {
  asm volatile("cp.async.bulk.global.shared::cta.bulk_group [%0], [%1], %2;" ::"l"(dst), "r"(src), "r"(bytes) : "memory");
}
__device__ __forceinline__ void bulk_wait_read() {
  asm volatile("cp.async.bulk.commit_group;\ncp.async.bulk.wait_group.read 0;" ::: "memory");
}

__device__ __forceinline__ void publish(void* dst, uint32_t src, uint32_t bytes, uint32_t bar) {
  bulk_store(dst, src, bytes);
  bulk_wait_read();
  bulk_load(src, dst, bytes, bar);
}

__device__ __forceinline__ void wg_fence() { asm volatile("wgmma.fence.sync.aligned;" ::: "memory"); }
__device__ __forceinline__ void wg_commit() { asm volatile("wgmma.commit_group.sync.aligned;" ::: "memory"); }
template <int N> __device__ __forceinline__ void wg_wait() { asm volatile("wgmma.wait_group.sync.aligned %0;" ::"n"(N) : "memory"); }
__device__ __forceinline__ uint32_t desc_lo(uint32_t addr, uint32_t lbo) { return ((addr & 0x3FFFF) >> 4) | ((lbo >> 4) << 16); }
constexpr uint32_t desc_hi(uint32_t sbo, uint32_t swz) { return (sbo >> 4) | (swz << 30); }
constexpr uint32_t HI_SW128 = desc_hi(1024, 1), HI_SW64 = desc_hi(512, 2), HI_SW32 = desc_hi(256, 3), HI_NONE = desc_hi(128, 0);
template <int N> __device__ __forceinline__ void pin(float* d) {
#pragma unroll
  for (int i = 0; i < N; i++) asm volatile("" : "+f"(d[i])::"memory");
}

__device__ __forceinline__ uint32_t lds32(uint32_t a) {
  uint32_t v;
  asm volatile("ld.volatile.shared.u32 %0, [%1];" : "=r"(v) : "r"(a) : "memory");
  return v;
}
__device__ __forceinline__ uint2 ldg64(const void* a) {
  uint2 v;
  asm volatile("ld.global.nc.v2.u32 {%0, %1}, [%2];" : "=r"(v.x), "=r"(v.y) : "l"(a) : "memory");
  return v;
}
__device__ __forceinline__ void ldsm4(uint32_t* r, uint32_t a) {
  asm volatile("ldmatrix.sync.aligned.m8n8.x4.shared.b16 {%0, %1, %2, %3}, [%4];"
               : "=r"(r[0]), "=r"(r[1]), "=r"(r[2]), "=r"(r[3]) : "r"(a) : "memory");
}
__device__ __forceinline__ void ldsm4t(uint32_t* r, uint32_t a) {
  asm volatile("ldmatrix.sync.aligned.m8n8.x4.trans.shared.b16 {%0, %1, %2, %3}, [%4];"
               : "=r"(r[0]), "=r"(r[1]), "=r"(r[2]), "=r"(r[3]) : "r"(a) : "memory");
}
__device__ __forceinline__ uint2 lds64(uint32_t a) {
  uint2 v;
  asm volatile("ld.shared.v2.u32 {%0, %1}, [%2];" : "=r"(v.x), "=r"(v.y) : "r"(a) : "memory");
  return v;
}
__device__ __forceinline__ uint4 lds128(uint32_t a) {
  uint4 v;
  asm volatile("ld.shared.v4.u32 {%0, %1, %2, %3}, [%4];" : "=r"(v.x), "=r"(v.y), "=r"(v.z), "=r"(v.w) : "r"(a) : "memory");
  return v;
}
__device__ __forceinline__ void sts128(uint32_t a, uint32_t x, uint32_t y, uint32_t z, uint32_t w) {
  asm volatile("st.shared.v4.u32 [%0], {%1, %2, %3, %4};" ::"r"(a), "r"(x), "r"(y), "r"(z), "r"(w) : "memory");
}
__device__ __forceinline__ void stsm4(uint32_t a, const uint32_t* r) {
  asm volatile("stmatrix.sync.aligned.m8n8.x4.shared.b16 [%0], {%1, %2, %3, %4};" ::"r"(a), "r"(r[0]), "r"(r[1]), "r"(r[2]), "r"(r[3]) : "memory");
}
__device__ __forceinline__ uint32_t pack2(float lo, float hi) {
  uint32_t r;
  asm("cvt.rn.bf16x2.f32 %0, %1, %2;" : "=r"(r) : "f"(hi), "f"(lo));
  return r;
}
__device__ __forceinline__ uint32_t movm(uint32_t a) {
  uint32_t d;
  asm volatile("movmatrix.sync.aligned.m8n8.trans.b16 %0, %1;" : "=r"(d) : "r"(a));
  return d;
}
__device__ __forceinline__ uint32_t bmul(uint32_t a, uint32_t b) {
  uint32_t d;
  asm("mul.rn.bf16x2 %0, %1, %2;" : "=r"(d) : "r"(a), "r"(b));
  return d;
}
__device__ __forceinline__ uint32_t badd(uint32_t a, uint32_t b) {
  uint32_t d;
  asm("add.rn.bf16x2 %0, %1, %2;" : "=r"(d) : "r"(a), "r"(b));
  return d;
}
__device__ __forceinline__ uint32_t bfma(uint32_t a, uint32_t b, uint32_t c) {
  uint32_t d;
  asm("fma.rn.bf16x2 %0, %1, %2, %3;" : "=r"(d) : "r"(a), "r"(b), "r"(c));
  return d;
}
__device__ __forceinline__ float bf_lo(uint32_t x) { return __uint_as_float(x << 16); }
__device__ __forceinline__ float bf_hi(uint32_t x) { return __uint_as_float(x & 0xFFFF0000u); }
__device__ __forceinline__ float ex2(float x) {
  float y;
  asm("ex2.approx.ftz.f32 %0, %1;" : "=f"(y) : "f"(x));
  return y;
}
__device__ __forceinline__ float rcp(float x) {
  float y;
  asm("rcp.approx.ftz.f32 %0, %1;" : "=f"(y) : "f"(x));
  return y;
}
__device__ __forceinline__ void mma16816(float* d, uint32_t a0, uint32_t a1, uint32_t a2, uint32_t a3, uint32_t b0, uint32_t b1) {
  asm volatile("mma.sync.aligned.m16n8k16.row.col.f32.bf16.bf16.f32 {%0, %1, %2, %3}, {%4, %5, %6, %7}, {%8, %9}, {%0, %1, %2, %3};"
               : "+f"(d[0]), "+f"(d[1]), "+f"(d[2]), "+f"(d[3])
               : "r"(a0), "r"(a1), "r"(a2), "r"(a3), "r"(b0), "r"(b1));
}
__device__ __forceinline__ void mma1688(float* d, uint32_t a0, uint32_t a1, uint32_t b0) {
  asm volatile("mma.sync.aligned.m16n8k8.row.col.f32.bf16.bf16.f32 {%0, %1, %2, %3}, {%4, %5}, {%6}, {%0, %1, %2, %3};"
               : "+f"(d[0]), "+f"(d[1]), "+f"(d[2]), "+f"(d[3])
               : "r"(a0), "r"(a1), "r"(b0));
}

template <int N> struct WgRS;
template <int N> struct WgSST;
template <> struct WgRS<32> {
  template <uint32_t HB>
  static __device__ __forceinline__ void mma(float* d, const uint32_t* a, uint32_t db) {
    asm volatile("{\n.reg .pred p;\n.reg .b64 db;\nsetp.ne.b32 p, %22, 0;\n"
      "mov.b64 db, {%20, %21};\n"
      "wgmma.mma_async.sync.aligned.m64n32k16.f32.bf16.bf16 {"
      "%0, %1, %2, %3, %4, %5, %6, %7, %8, %9, %10, %11, %12, %13, %14, %15"
      "}, {%16, %17, %18, %19}, db, p, 1, 1, 1;\n}\n"
      : "+f"(d[0]), "+f"(d[1]), "+f"(d[2]), "+f"(d[3]), "+f"(d[4]), "+f"(d[5]), "+f"(d[6]), "+f"(d[7]),
        "+f"(d[8]), "+f"(d[9]), "+f"(d[10]), "+f"(d[11]), "+f"(d[12]), "+f"(d[13]), "+f"(d[14]), "+f"(d[15])
      : "r"(a[0]), "r"(a[1]), "r"(a[2]), "r"(a[3]), "r"(db), "n"(HB), "n"(1));
  }
  template <uint32_t HB>
  static __device__ __forceinline__ void set(float* d, const uint32_t* a, uint32_t db) {
    asm volatile("{\n.reg .pred p;\n.reg .b64 db;\nsetp.ne.b32 p, %22, 0;\n"
      "mov.b64 db, {%20, %21};\n"
      "wgmma.mma_async.sync.aligned.m64n32k16.f32.bf16.bf16 {"
      "%0, %1, %2, %3, %4, %5, %6, %7, %8, %9, %10, %11, %12, %13, %14, %15"
      "}, {%16, %17, %18, %19}, db, p, 1, 1, 1;\n}\n"
      : "=f"(d[0]), "=f"(d[1]), "=f"(d[2]), "=f"(d[3]), "=f"(d[4]), "=f"(d[5]), "=f"(d[6]), "=f"(d[7]),
        "=f"(d[8]), "=f"(d[9]), "=f"(d[10]), "=f"(d[11]), "=f"(d[12]), "=f"(d[13]), "=f"(d[14]), "=f"(d[15])
      : "r"(a[0]), "r"(a[1]), "r"(a[2]), "r"(a[3]), "r"(db), "n"(HB), "n"(0));
  }
};
template <> struct WgRS<64> {
  template <uint32_t HB>
  static __device__ __forceinline__ void mma(float* d, const uint32_t* a, uint32_t db) {
    asm volatile("{\n.reg .pred p;\n.reg .b64 db;\nsetp.ne.b32 p, %38, 0;\n"
      "mov.b64 db, {%36, %37};\n"
      "wgmma.mma_async.sync.aligned.m64n64k16.f32.bf16.bf16 {"
      "%0, %1, %2, %3, %4, %5, %6, %7, %8, %9, %10, %11, %12, %13, %14, %15, "
      "%16, %17, %18, %19, %20, %21, %22, %23, %24, %25, %26, %27, %28, %29, %30, %31"
      "}, {%32, %33, %34, %35}, db, p, 1, 1, 1;\n}\n"
      : "+f"(d[0]), "+f"(d[1]), "+f"(d[2]), "+f"(d[3]), "+f"(d[4]), "+f"(d[5]), "+f"(d[6]), "+f"(d[7]),
        "+f"(d[8]), "+f"(d[9]), "+f"(d[10]), "+f"(d[11]), "+f"(d[12]), "+f"(d[13]), "+f"(d[14]), "+f"(d[15]),
        "+f"(d[16]), "+f"(d[17]), "+f"(d[18]), "+f"(d[19]), "+f"(d[20]), "+f"(d[21]), "+f"(d[22]), "+f"(d[23]),
        "+f"(d[24]), "+f"(d[25]), "+f"(d[26]), "+f"(d[27]), "+f"(d[28]), "+f"(d[29]), "+f"(d[30]), "+f"(d[31])
      : "r"(a[0]), "r"(a[1]), "r"(a[2]), "r"(a[3]), "r"(db), "n"(HB), "n"(1));
  }
  template <uint32_t HB>
  static __device__ __forceinline__ void set(float* d, const uint32_t* a, uint32_t db) {
    asm volatile("{\n.reg .pred p;\n.reg .b64 db;\nsetp.ne.b32 p, %38, 0;\n"
      "mov.b64 db, {%36, %37};\n"
      "wgmma.mma_async.sync.aligned.m64n64k16.f32.bf16.bf16 {"
      "%0, %1, %2, %3, %4, %5, %6, %7, %8, %9, %10, %11, %12, %13, %14, %15, "
      "%16, %17, %18, %19, %20, %21, %22, %23, %24, %25, %26, %27, %28, %29, %30, %31"
      "}, {%32, %33, %34, %35}, db, p, 1, 1, 1;\n}\n"
      : "=f"(d[0]), "=f"(d[1]), "=f"(d[2]), "=f"(d[3]), "=f"(d[4]), "=f"(d[5]), "=f"(d[6]), "=f"(d[7]),
        "=f"(d[8]), "=f"(d[9]), "=f"(d[10]), "=f"(d[11]), "=f"(d[12]), "=f"(d[13]), "=f"(d[14]), "=f"(d[15]),
        "=f"(d[16]), "=f"(d[17]), "=f"(d[18]), "=f"(d[19]), "=f"(d[20]), "=f"(d[21]), "=f"(d[22]), "=f"(d[23]),
        "=f"(d[24]), "=f"(d[25]), "=f"(d[26]), "=f"(d[27]), "=f"(d[28]), "=f"(d[29]), "=f"(d[30]), "=f"(d[31])
      : "r"(a[0]), "r"(a[1]), "r"(a[2]), "r"(a[3]), "r"(db), "n"(HB), "n"(0));
  }
};
template <> struct WgSST<48> {
  template <uint32_t HA, uint32_t HB>
  static __device__ __forceinline__ void mma(float* d, uint32_t da, uint32_t db, int sc) {
    asm volatile("{\n.reg .pred p;\n.reg .b64 da, db;\nsetp.ne.b32 p, %28, 0;\n"
      "mov.b64 da, {%24, %25};\nmov.b64 db, {%26, %27};\n"
      "wgmma.mma_async.sync.aligned.m64n48k16.f32.bf16.bf16 {"
      "%0, %1, %2, %3, %4, %5, %6, %7, %8, %9, %10, %11, %12, %13, %14, %15, "
      "%16, %17, %18, %19, %20, %21, %22, %23"
      "}, da, db, p, 1, 1, 0, 1;\n}\n"
      : "+f"(d[0]), "+f"(d[1]), "+f"(d[2]), "+f"(d[3]), "+f"(d[4]), "+f"(d[5]), "+f"(d[6]), "+f"(d[7]),
        "+f"(d[8]), "+f"(d[9]), "+f"(d[10]), "+f"(d[11]), "+f"(d[12]), "+f"(d[13]), "+f"(d[14]), "+f"(d[15]),
        "+f"(d[16]), "+f"(d[17]), "+f"(d[18]), "+f"(d[19]), "+f"(d[20]), "+f"(d[21]), "+f"(d[22]), "+f"(d[23])
      : "r"(da), "n"(HA), "r"(db), "n"(HB), "r"(sc));
  }
};
template <> struct WgSST<80> {
  template <uint32_t HA, uint32_t HB>
  static __device__ __forceinline__ void mma(float* d, uint32_t da, uint32_t db, int sc) {
    asm volatile("{\n.reg .pred p;\n.reg .b64 da, db;\nsetp.ne.b32 p, %44, 0;\n"
      "mov.b64 da, {%40, %41};\nmov.b64 db, {%42, %43};\n"
      "wgmma.mma_async.sync.aligned.m64n80k16.f32.bf16.bf16 {"
      "%0, %1, %2, %3, %4, %5, %6, %7, %8, %9, %10, %11, %12, %13, %14, %15, "
      "%16, %17, %18, %19, %20, %21, %22, %23, %24, %25, %26, %27, %28, %29, %30, %31, "
      "%32, %33, %34, %35, %36, %37, %38, %39"
      "}, da, db, p, 1, 1, 0, 1;\n}\n"
      : "+f"(d[0]), "+f"(d[1]), "+f"(d[2]), "+f"(d[3]), "+f"(d[4]), "+f"(d[5]), "+f"(d[6]), "+f"(d[7]),
        "+f"(d[8]), "+f"(d[9]), "+f"(d[10]), "+f"(d[11]), "+f"(d[12]), "+f"(d[13]), "+f"(d[14]), "+f"(d[15]),
        "+f"(d[16]), "+f"(d[17]), "+f"(d[18]), "+f"(d[19]), "+f"(d[20]), "+f"(d[21]), "+f"(d[22]), "+f"(d[23]),
        "+f"(d[24]), "+f"(d[25]), "+f"(d[26]), "+f"(d[27]), "+f"(d[28]), "+f"(d[29]), "+f"(d[30]), "+f"(d[31]),
        "+f"(d[32]), "+f"(d[33]), "+f"(d[34]), "+f"(d[35]), "+f"(d[36]), "+f"(d[37]), "+f"(d[38]), "+f"(d[39])
      : "r"(da), "n"(HA), "r"(db), "n"(HB), "r"(sc));
  }
};
template <> struct WgSST<192> {
  template <uint32_t HA, uint32_t HB>
  static __device__ __forceinline__ void mma(float* d, uint32_t da, uint32_t db, int sc) {
    asm volatile("{\n.reg .pred p;\n.reg .b64 da, db;\nsetp.ne.b32 p, %100, 0;\n"
      "mov.b64 da, {%96, %97};\nmov.b64 db, {%98, %99};\n"
      "wgmma.mma_async.sync.aligned.m64n192k16.f32.bf16.bf16 {"
      "%0, %1, %2, %3, %4, %5, %6, %7, %8, %9, %10, %11, %12, %13, %14, %15, "
      "%16, %17, %18, %19, %20, %21, %22, %23, %24, %25, %26, %27, %28, %29, %30, %31, "
      "%32, %33, %34, %35, %36, %37, %38, %39, %40, %41, %42, %43, %44, %45, %46, %47, "
      "%48, %49, %50, %51, %52, %53, %54, %55, %56, %57, %58, %59, %60, %61, %62, %63, "
      "%64, %65, %66, %67, %68, %69, %70, %71, %72, %73, %74, %75, %76, %77, %78, %79, "
      "%80, %81, %82, %83, %84, %85, %86, %87, %88, %89, %90, %91, %92, %93, %94, %95"
      "}, da, db, p, 1, 1, 0, 1;\n}\n"
      : "+f"(d[0]), "+f"(d[1]), "+f"(d[2]), "+f"(d[3]), "+f"(d[4]), "+f"(d[5]), "+f"(d[6]), "+f"(d[7]),
        "+f"(d[8]), "+f"(d[9]), "+f"(d[10]), "+f"(d[11]), "+f"(d[12]), "+f"(d[13]), "+f"(d[14]), "+f"(d[15]),
        "+f"(d[16]), "+f"(d[17]), "+f"(d[18]), "+f"(d[19]), "+f"(d[20]), "+f"(d[21]), "+f"(d[22]), "+f"(d[23]),
        "+f"(d[24]), "+f"(d[25]), "+f"(d[26]), "+f"(d[27]), "+f"(d[28]), "+f"(d[29]), "+f"(d[30]), "+f"(d[31]),
        "+f"(d[32]), "+f"(d[33]), "+f"(d[34]), "+f"(d[35]), "+f"(d[36]), "+f"(d[37]), "+f"(d[38]), "+f"(d[39]),
        "+f"(d[40]), "+f"(d[41]), "+f"(d[42]), "+f"(d[43]), "+f"(d[44]), "+f"(d[45]), "+f"(d[46]), "+f"(d[47]),
        "+f"(d[48]), "+f"(d[49]), "+f"(d[50]), "+f"(d[51]), "+f"(d[52]), "+f"(d[53]), "+f"(d[54]), "+f"(d[55]),
        "+f"(d[56]), "+f"(d[57]), "+f"(d[58]), "+f"(d[59]), "+f"(d[60]), "+f"(d[61]), "+f"(d[62]), "+f"(d[63]),
        "+f"(d[64]), "+f"(d[65]), "+f"(d[66]), "+f"(d[67]), "+f"(d[68]), "+f"(d[69]), "+f"(d[70]), "+f"(d[71]),
        "+f"(d[72]), "+f"(d[73]), "+f"(d[74]), "+f"(d[75]), "+f"(d[76]), "+f"(d[77]), "+f"(d[78]), "+f"(d[79]),
        "+f"(d[80]), "+f"(d[81]), "+f"(d[82]), "+f"(d[83]), "+f"(d[84]), "+f"(d[85]), "+f"(d[86]), "+f"(d[87]),
        "+f"(d[88]), "+f"(d[89]), "+f"(d[90]), "+f"(d[91]), "+f"(d[92]), "+f"(d[93]), "+f"(d[94]), "+f"(d[95])
      : "r"(da), "n"(HA), "r"(db), "n"(HB), "r"(sc));
  }
};

struct FftConst {
  uint32_t f[2][4], fi[4][4];
  uint32_t ta[2][2], tb[2][2];
};
__device__ __forceinline__ void cis(int m, float scale, float& c, float& s) {
  const float a = (float)m * (-6.283185307179586f * scale);
  c = __cosf(a);
  s = __sinf(a);
}
__device__ __forceinline__ void fft_tables(uint32_t (&v)[12], int tw) {
  const int row = tw >> 2, ch = tw & 3;
#pragma unroll
  for (int i = 0; i < 4; i++) {
    float c[2], s[2], x[2];
#pragma unroll
    for (int e = 0; e < 2; e++) {
      cis((((32 * (8 * ch + 2 * i + e) + 15) * (4 * row - 63) + 2048) & 4095) - 2048, 1.f / 4096, c[e], s[e]);
      float gc, gs;
      cis((((row & 15) * (8 * (ch & 1) + 2 * i + e) + 8) & 15) - 8, 1.f / 16, gc, gs);
      x[e] = (row >> 4) == (ch >> 1) ? gc : (ch >> 1) ? gs : -gs;
    }
    v[i] = pack2(c[0] * 0.125f, c[1] * 0.125f);
    v[4 + i] = pack2(s[0] * 0.125f, s[1] * 0.125f);
    v[8 + i] = pack2(x[0], x[1]);
  }
#pragma unroll
  for (int i = 0; i < 12; i++) asm volatile("" : "+r"(v[i]));
}
__device__ __forceinline__ void fft_tables_store(const uint32_t (&v)[12], uint32_t sb, int tw) {
  const int row = tw >> 2;
  const uint32_t x = ((tw ^ (row >> 1)) & 3) << 4, a = sb + OFF_FT + (16 * (row >> 3) + (row & 7)) * 64 + x;
  sts128(a, v[0], v[1], v[2], v[3]);
  sts128(a + 512, v[4], v[5], v[6], v[7]);
  sts128(sb + OFF_GT + row * 64 + x, v[8], v[9], v[10], v[11]);
}
__device__ __forceinline__ void fft_twiddles(uint32_t (&v)[2], int tw) {
  float a[2], s[2];
#pragma unroll
  for (int i = 0; i < 2; i++) {
    float c;
    cis((2 * (2 * (tw & 3) + i) - 15) * (4 * (tw >> 2) - 63), 1.f / 4096, c, s[i]);
    a[i] = __fdividef(-s[i], 1.f + c);
  }
  v[0] = pack2(a[0], a[1]);
  v[1] = pack2(s[0], s[1]);
  asm volatile("" : "+r"(v[0]), "+r"(v[1]));
}
__device__ __forceinline__ void fft_matrices(FftConst& k, uint32_t sb, int w, int lane) {
  const uint32_t x = (lane >> 1) & 3;
  const uint2 t0 = lds64(sb + OFF_TT + 256 * w + 8 * lane), t1 = lds64(sb + OFF_TT + 256 * w + 8 * (lane ^ 3));
  k.ta[0][0] = t0.x;
  k.tb[0][0] = t0.y;
  k.ta[1][1] = __byte_perm(t1.x, 0, 0x1032);
  k.tb[1][1] = __byte_perm(t1.y, 0, 0x1032);
#pragma unroll
  for (int j = 0; j < 2; j++) {
    k.ta[1 - j][j] = k.ta[j][j] ^ 0x80008000u;
    k.tb[1 - j][j] = k.tb[j][j] ^ 0x80008000u;
    asm volatile("" : "+r"(k.ta[0][j]), "+r"(k.tb[0][j]), "+r"(k.ta[1][j]), "+r"(k.tb[1][j]));
  }
#pragma unroll
  for (int i = 0; i < 2; i++) {
    ldsm4(k.f[i], sb + OFF_FT + (16 * w + (lane & 15)) * 64 + (((2 * i + (lane >> 4)) ^ x) << 4));
    ldsm4t(k.fi[i], sb + OFF_FT + (32 * i + lane) * 64 + ((w ^ x) << 4));
#pragma unroll
    for (int j = 0; j < 4; j++) {
      k.fi[2 + i][j] = (j & 1) ? k.fi[i][j - 1] ^ 0x80008000u : k.fi[i][j + 1];
      asm volatile("" : "+r"(k.fi[2 + i][j]));
    }
  }
}
__device__ __forceinline__ void rot(uint32_t& x, uint32_t& y, uint32_t a, uint32_t b) {
  x = bfma(a, y, x);
  y = bfma(b, x, y);
  x = bfma(a, y, x);
}
__device__ __forceinline__ void twiddle_fwd(uint32_t (&a)[4][4], float* d, const FftConst& k) {
#pragma unroll
  for (int q = 0; q < 4; q++)
#pragma unroll
    for (int j = 0; j < 2; j++) {
      const float* x = d + 8 * q + 4 * j;
      uint32_t re = pack2(x[0], x[1]), im = pack2(x[2], x[3]);
      rot(re, im, k.ta[0][j], k.tb[0][j]);
      a[q & 2][2 * j + (q & 1)] = re;
      a[(q & 2) + 1][2 * j + (q & 1)] = im;
    }
}
__device__ __forceinline__ void g_step(float* d, const uint32_t (&a)[4][4], uint32_t dre, uint32_t dim) {
  WgRS<32>::set<HI_SW64>(d, a[0], dre);
  WgRS<32>::set<HI_SW64>(d + 16, a[2], dre);
  WgRS<32>::mma<HI_SW64>(d, a[1], dim);
  WgRS<32>::mma<HI_SW64>(d + 16, a[3], dim);
  wg_commit();
}

__device__ __forceinline__ void products(uint32_t (&a)[4][4], const float* H, const float* U, int p) {
#pragma unroll
  for (int j = 0; j < 2; j++)
#pragma unroll
    for (int m = 2 * p; m < 2 * p + 2; m++) {
      float pr[2], pi[2];
#pragma unroll
      for (int x = 0; x < 2; x++)
#pragma unroll
        for (int q = 0; q <= m; q++) {
          const int ih = 16 * (q >> 1) + 2 * (q & 1) + 4 * j + x, iu = 16 * ((m - q) >> 1) + 2 * ((m - q) & 1) + 4 * j + x;
          pr[x] = q ? fmaf(H[ih], U[iu], pr[x]) : H[ih] * U[iu];
          pi[x] = q ? fmaf(H[ih], U[iu + 8], pi[x]) : H[ih] * U[iu + 8];
          pr[x] = fmaf(-H[ih + 8], U[iu + 8], pr[x]);
          pi[x] = fmaf(H[ih + 8], U[iu], pi[x]);
        }
      a[m & 2][2 * j + (m & 1)] = pack2(pr[0], pr[1]);
      a[(m & 2) + 1][2 * j + (m & 1)] = pack2(pi[0], pi[1]);
    }
}

__device__ __forceinline__ void conv_channel(const FftConst& k, uint32_t sb, int c, int wg, int w, int lane) {
  const uint32_t cb = sb + off_ch(c), bars = sb + OFF_BAR;
  const uint32_t du = desc_lo(cb, 1024), dg = desc_lo(sb + OFF_GT, 16), dz = desc_lo(cb + U_BYTES, 16);
  float U[32], H[32];
  uint32_t a[4][4], e[4][4];
  const float dv = __uint_as_float(lds32(sb + OFF_D + 4 * c));
  wg_fence();
  WgRS<64>::set<HI_SW32>(H, k.f[0], du + 256);
  WgRS<64>::mma<HI_SW32>(H, k.f[1], du + 256 + 32);
  wg_commit();
  wg_wait<0>();
  pin<32>(H);
  twiddle_fwd(a, H, k);
  mbar_wait(bars + 8 * (B_U + (c < 3 ? c : 3)), 0);
  TSM(w == 0 && c < 3, 7 + wg);
  wg_fence();
  WgRS<64>::set<HI_SW32>(U, k.f[0], du);
  WgRS<64>::mma<HI_SW32>(U, k.f[1], du + 32);
  wg_commit();
  g_step(H, a, dg, dg + 64);
  wg_wait<1>();
  pin<32>(U);
  twiddle_fwd(e, U, k);
  wg_fence();
  g_step(U, e, dg, dg + 64);
  wg_wait<0>();
  pin<32>(U);
  pin<32>(H);
#pragma unroll
  for (int j = 0; j < 4; j++) H[4 * (j >> 1) + (j & 1)] += dv;
  float V[32];
#pragma unroll
  for (int p = 0; p < 2; p++) {
    products(a, H, U, p);
    wg_fence();
    WgRS<32>::set<HI_SW64>(V + 16 * p, a[2 * p], dg + 64);
    WgRS<32>::mma<HI_SW64>(V + 16 * p, a[2 * p + 1], dg);
    wg_commit();
  }
  const uint32_t za = cb + U_BYTES + (8 * w + (lane & 7)) * 128 + (((lane >> 3) ^ (lane & 7)) << 4);
  const uint32_t ya = cb + (lane >> 4) * 1024 + (8 * w + (lane & 7)) * 32 + ((((lane >> 3) ^ (lane >> 2)) & 1) << 4);
  wg_sync(1 + wg);
#pragma unroll
  for (int p = 0; p < 2; p++) {
    if (p == 0) wg_wait<1>();
    else wg_wait<0>();
    pin<16>(V + 16 * p);
#pragma unroll
    for (int i = 0; i < 4; i++) {
      const int j = i & 1;
      const float* x = V + 16 * p + 4 * j + (i & 2);
      e[p][i] = pack2(x[8], x[9]);
      e[2 + p][i] = pack2(x[0], x[1]);
      rot(e[p][i], e[2 + p][i], k.ta[1][j], k.tb[1][j]);
    }
    stsm4(za ^ (64 * p), e[p]);
    stsm4((za ^ (64 * p)) + 4096, e[2 + p]);
  }
  fence_async_smem();
  wg_sync(1 + wg);
  wg_fence();
  WgRS<64>::set<HI_SW128>(H, k.fi[0], dz);
#pragma unroll
  for (int ks = 1; ks < 4; ks++) WgRS<64>::mma<HI_SW128>(H, k.fi[ks], dz + 128 * ks);
  wg_commit();
  wg_wait<0>();
  pin<32>(H);
  if (lane == 0) mbar_arrive(bars + 8 * B_CVD);
  TSIF(w == 0, 88 + c);
#pragma unroll
  for (int j = 0; j < 8; j++)
    a[j >> 2][j & 3] = j < 2 ? pack2(H[4 * j], H[4 * j + 1]) : pack2(H[4 * j] + H[4 * j - 6], H[4 * j + 1] + H[4 * j - 5]);
  stsm4(ya, a[0]);
  stsm4(ya + 2048, a[1]);
  fence_async_smem();
  __syncwarp();
}

__device__ __forceinline__ void prep_slab(uint4* res, const uint2* sw, uint32_t sb, int slab, int w, int lane) {
  const int t = lane & 3, tp = (lane & 7) >> 1, pos = 8 * tp + 2 * (((lane >> 3) + tp) & 3) + (lane & 1);
  const uint32_t base = sb + OFF_KVS + slab * KVS_BYTES + pos * 128;
  uint32_t kk[2][4][4], vv[2][4];
  mbar_wait(sb + OFF_BAR + 8 * (B_KV + slab), 0);
#pragma unroll
  for (int h = 0; h < 2; h++) {
#pragma unroll
    for (int j = 0; j < 4; j++) {
      const uint32_t a = base + 128 * j;
      ldsm4t(kk[h][j], a + (((w + 4 * h) ^ ((a >> 7) & 7)) << 4));
    }
    const uint32_t a = base + KVS_V;
    ldsm4t(vv[h], a + (((w + 4 * h) ^ ((a >> 7) & 7)) << 4));
  }
#pragma unroll
  for (int h = 0; h < 2; h++) {
    uint32_t (&k)[4][4] = kk[h];
    uint32_t (&v)[4] = vv[h];
    const uint32_t w0 = __byte_perm(sw[h].x, 0, 0x1010), w1 = __byte_perm(sw[h].x, 0, 0x3232);
    const uint32_t w2 = __byte_perm(sw[h].y, 0, 0x1010), w3 = __byte_perm(sw[h].y, 0, 0x3232);
#pragma unroll
    for (int m = 0; m < 4; m++)
      v[m] = bmul(badd(badd(badd(bmul(k[0][m], w3), bmul(k[1][m], w2)), bmul(k[2][m], w1)), bmul(k[3][m], w0)), v[m]);
    uint32_t a[4];
#pragma unroll
    for (int m = 0; m < 4; m++) a[m] = (t & 1) ? v[(m + 3) & 3] : v[m];
    res[h] = (t & 2) ? make_uint4(a[2], a[3], a[0], a[1]) : make_uint4(a[0], a[1], a[2], a[3]);
  }
}

__device__ __forceinline__ void prep_gate(const Params& p, uint32_t sb, int b, int w, int lane) {
  uint2 gw[5], x[4][5];
#pragma unroll
  for (int j = 0; j < 5; j++) gw[j] = ldg64(reinterpret_cast<const uint2*>(p.gate_w) + lane + 32 * j);
#pragma unroll
  for (int i = 0; i < 4; i++)
#pragma unroll
    for (int j = 0; j < 5; j++)
      x[i][j] = ldg64(reinterpret_cast<const uint2*>(p.q) + (16 * b + 4 * w + i) * (DIM / 4) + lane + 32 * j);
  float s[4];
#pragma unroll
  for (int i = 0; i < 4; i++) {
    s[i] = 0.f;
#pragma unroll
    for (int j = 0; j < 5; j++) {
      const uint32_t m0 = bmul(x[i][j].x, gw[j].x), m1 = bmul(x[i][j].y, gw[j].y);
      s[i] += (bf_lo(m0) + bf_hi(m0)) + (bf_lo(m1) + bf_hi(m1));
    }
  }
  const bool h = lane & 16, q = lane & 8;
  const float a = (h ? s[2] : s[0]) + __shfl_xor_sync(0xffffffffu, h ? s[0] : s[2], 16);
  const float c = (h ? s[3] : s[1]) + __shfl_xor_sync(0xffffffffu, h ? s[1] : s[3], 16);
  float z = (q ? c : a) + __shfl_xor_sync(0xffffffffu, q ? a : c, 8);
#pragma unroll
  for (int o = 4; o > 0; o >>= 1) z += __shfl_xor_sync(0xffffffffu, z, o);
  z = bf_lo(pack2(z, 0.f));
  z = bf_lo(pack2(__fdividef(1.f, 1.f + __expf(-z)), 0.f));
  mbar_wait(sb + OFF_BAR + 8 * B_S3, 0);
  if ((lane & 7) == 0) asm volatile("st.shared.f32 [%0], %1;" ::"r"(sb + OFF_GATE + 64 * (b & 7) + 16 * w + (lane >> 1)), "f"(z) : "memory");
  fence_async_smem();
}

__device__ __forceinline__ uint32_t bmax(uint32_t a, uint32_t b) {
  uint32_t d;
  asm("max.bf16x2 %0, %1, %2;" : "=r"(d) : "r"(a), "r"(b));
  return d;
}
__device__ __forceinline__ void softmax_two(const float (&l)[2][2], uint32_t& p0, uint32_t& p1) {
  constexpr float kScale = 0.22360679774997896f, kLog2e = 1.4426950408889634f;
  const uint32_t r0 = pack2(l[0][0], l[1][0]), r1 = pack2(l[0][1], l[1][1]);
  const uint32_t x0 = pack2(bf_lo(r0) * kScale, bf_hi(r0) * kScale), x1 = pack2(bf_lo(r1) * kScale, bf_hi(r1) * kScale);
  uint32_t m = bmax(x0, x1);
  m = bmax(m, __shfl_xor_sync(0xffffffffu, m, 1));
  m = bmax(m, __shfl_xor_sync(0xffffffffu, m, 2));
  const float m0 = bf_lo(m) * kLog2e, m1 = bf_hi(m) * kLog2e;
  p0 = pack2(ex2(bf_lo(x0) * kLog2e - m0), ex2(bf_lo(x1) * kLog2e - m0));
  p1 = pack2(ex2(bf_hi(x0) * kLog2e - m1), ex2(bf_hi(x1) * kLog2e - m1));
}

__device__ __forceinline__ void halo_read(uint32_t (&kpv)[10], uint32_t (&vpv)[10], uint32_t (&tg)[7], const uint4* hp) {
#pragma unroll
  for (int j = 0; j < 7; j++) {
    uint32_t x0, x1, x2;
    asm volatile("ld.relaxed.gpu.global.v4.u32 {%0, %1, %2, %3}, [%4];"
                 : "=r"(x0), "=r"(x1), "=r"(x2), "=r"(tg[j]) : "l"(hp + 32 * j) : "memory");
    if (j < 4) kpv[3 * j] = x0; else vpv[3 * j - 10] = x0;
    if (j < 3) kpv[3 * j + 1] = x1; else vpv[3 * j - 9] = x1;
    if (j < 3) kpv[3 * j + 2] = x2; else if (j < 6) vpv[3 * j - 8] = x2;
  }
}

template <int ROT>
__device__ __forceinline__ void pack_qkv(const float* acc, uint32_t (&qlo)[10], uint32_t (&qhi)[10], uint32_t (&klo)[10],
                                         uint32_t (&khi)[10], uint32_t (&vlo)[10], uint32_t (&vhi)[10]) {
#pragma unroll
  for (int j = 0; j < 10; j++) {
    const int x = (j + ROT) % 10, tq = x < 8 ? x : 16 + x, tk = x < 8 ? 8 + x : 18 + x, tv = x < 8 ? 16 + x : 20 + x;
    khi[j] = pack2(acc[4 * tk + 2], acc[4 * tk + 3]);
    vhi[j] = movm(pack2(acc[4 * tv + 2], acc[4 * tv + 3]));
    qlo[j] = pack2(acc[4 * tq], acc[4 * tq + 1]);
    qhi[j] = pack2(acc[4 * tq + 2], acc[4 * tq + 3]);
    klo[j] = pack2(acc[4 * tk], acc[4 * tk + 1]);
    vlo[j] = pack2(acc[4 * tv], acc[4 * tv + 1]);
    asm volatile("" : "+r"(khi[j]), "+r"(qlo[j]), "+r"(qhi[j]), "+r"(klo[j]), "+r"(vlo[j]));
  }
}

template <int ROT> __device__ __forceinline__ void halo_send(const float* acc, uint4* ho, uint32_t tag) {
#pragma unroll
  for (int j = 0; j < 7; j++) {
    uint32_t x[3];
#pragma unroll
    for (int e = 0; e < 3; e++) {
      const int i = 3 * j + e, y = (i % 10 + ROT) % 10, tk = y < 8 ? 8 + y : 18 + y, tv = y < 8 ? 16 + y : 20 + y;
      x[e] = i < 10 ? pack2(acc[4 * tk + 2], acc[4 * tk + 3]) : i < 20 ? movm(pack2(acc[4 * tv + 2], acc[4 * tv + 3])) : 0u;
    }
    asm volatile("st.relaxed.gpu.global.v4.u32 [%0], {%1, %2, %3, %4};" ::"l"(ho + 32 * j), "r"(x[0]), "r"(x[1]), "r"(x[2]), "r"(tag) : "memory");
  }
}

__device__ __forceinline__ void attention(float* acc, uint32_t sb, int b, int par, int w, int lane, uint32_t tag) {
  const int g = lane >> 2, t = lane & 3;
  uint32_t klo[10], khi[10], vlo[10], vhi[10], qlo[10], qhi[10], kpv[10], vpv[10];
  if (w == 3 && b < NCTA - 8) {
    uint4* ho = g_halo + (b * 2 + par) * 224 + lane;
    if (tail_first(b & 7)) halo_send<8>(acc, ho, tag);
    else halo_send<0>(acc, ho, tag);
    TSIF(par == 0, 76);
    pin<120>(acc);
  }
  if (tail_first(b & 7)) pack_qkv<8>(acc, qlo, qhi, klo, khi, vlo, vhi);
  else pack_qkv<0>(acc, qlo, qhi, klo, khi, vlo, vhi);
  const uint32_t xa = sb + OFF_KVX + (par * 3) * 2560 + lane * 16;
  if (w < 3) {
    sts128(xa + w * 2560, khi[0], khi[1], khi[2], khi[3]);
    sts128(xa + w * 2560 + 512, khi[4], khi[5], khi[6], khi[7]);
    sts128(xa + w * 2560 + 1024, khi[8], khi[9], vhi[0], vhi[1]);
    sts128(xa + w * 2560 + 1536, vhi[2], vhi[3], vhi[4], vhi[5]);
    sts128(xa + w * 2560 + 2048, vhi[6], vhi[7], vhi[8], vhi[9]);
  }
  TSIF(par == 0 && w == 1, 64);
#pragma unroll
  for (int j = 0; j < 10; j++) vlo[j] = movm(vlo[j]);
  const bool far0 = 2 * t > g, far1 = 2 * t + 1 > g;
  const uint32_t mfar = (far0 ? 0x0000FFFFu : 0u) | (far1 ? 0xFFFF0000u : 0u);
  float slo[4][2], lg[2][2];
  uint32_t phi[4], plo[4], qml[4], qmh[4];
#pragma unroll
  for (int h = 0; h < 4; h++) {
    const int f = h == 0 ? 0 : h == 1 ? 3 : h == 2 ? 5 : 8, hf = h < 2 ? 2 : 7;
    const bool mine = (h & 1) ? t >= 2 : t < 2;
    qml[h] = mine ? qlo[hf] : 0u;
    qmh[h] = mine ? qhi[hf] : 0u;
    float a[4] = {0.f, 0.f, 0.f, 0.f}, c[4] = {0.f, 0.f, 0.f, 0.f};
    mma16816(a, qlo[f], qhi[f], qlo[f + 1], qhi[f + 1], klo[f], klo[f + 1]);
    mma16816(c, qlo[f], qhi[f], qlo[f + 1], qhi[f + 1], khi[f], khi[f + 1]);
    mma1688(a, qml[h], qmh[h], klo[hf]);
    mma1688(c, qml[h], qmh[h], khi[hf]);
    slo[h][0] = a[0];
    slo[h][1] = a[1];
    lg[h & 1][0] = far0 ? a[2] : c[2];
    lg[h & 1][1] = far1 ? a[3] : c[3];
    if (h & 1) softmax_two(lg, phi[h - 1], phi[h]);
  }
  TSIF(par == 0 && w == 1, 65);
  wg_sync(1 + par);
  TSIF(par == 0 && w == 1, 66);
  const bool nohist = (w == 0) && (b < 8);
  const uint4* hp = g_halo + ((b - 8) * 2 + par) * 224 + lane;
  uint32_t tg[7];
  if (w > 0) {
    const uint4 v0 = lds128(xa + (w - 1) * 2560), v1 = lds128(xa + (w - 1) * 2560 + 512), v2 = lds128(xa + (w - 1) * 2560 + 1024);
    const uint4 v3 = lds128(xa + (w - 1) * 2560 + 1536), v4 = lds128(xa + (w - 1) * 2560 + 2048);
    kpv[0] = v0.x; kpv[1] = v0.y; kpv[2] = v0.z; kpv[3] = v0.w; kpv[4] = v1.x; kpv[5] = v1.y; kpv[6] = v1.z; kpv[7] = v1.w;
    kpv[8] = v2.x; kpv[9] = v2.y; vpv[0] = v2.z; vpv[1] = v2.w; vpv[2] = v3.x; vpv[3] = v3.y; vpv[4] = v3.z; vpv[5] = v3.w;
    vpv[6] = v4.x; vpv[7] = v4.y; vpv[8] = v4.z; vpv[9] = v4.w;
  } else if (nohist) {
#pragma unroll
    for (int j = 0; j < 10; j++) kpv[j] = vpv[j] = 0u;
  } else {
    TSIF(par == 0, 77);
    halo_read(kpv, vpv, tg, hp);
  }
  if (w == 0 && !nohist) {
    int spins = 0;
    while (true) {
      bool ok = true;
#pragma unroll
      for (int j = 0; j < 7; j++) ok = ok && tg[j] == tag;
      if (__all_sync(0xffffffffu, ok) || ++spins > SPIN_LIMIT) break;
      halo_read(kpv, vpv, tg, hp);
    }
    TSIF(par == 0, 79);
  }
#pragma unroll
  for (int h = 0; h < 4; h++) {
    const int f = h == 0 ? 0 : h == 1 ? 3 : h == 2 ? 5 : 8, hf = h < 2 ? 2 : 7;
    float a[4] = {0.f, 0.f, 0.f, 0.f};
    mma16816(a, qlo[f], qhi[f], qlo[f + 1], qhi[f + 1], kpv[f], kpv[f + 1]);
    mma1688(a, qml[h], qmh[h], kpv[hf]);
    const float ninf = __int_as_float(0xff800000);
    lg[h & 1][0] = far0 ? (nohist ? ninf : a[0]) : slo[h][0];
    lg[h & 1][1] = far1 ? (nohist ? ninf : a[1]) : slo[h][1];
    if (h & 1) softmax_two(lg, plo[h - 1], plo[h]);
  }
  TSIF(par == 0 && w <= 1, 67 + w);
  uint32_t ov[20];
#pragma unroll
  for (int hp = 0; hp < 2; hp++) {
    const int hf = hp ? 7 : 2;
    float sh[4] = {0.f, 0.f, 0.f, 0.f}, i0 = 0.f, i1 = 0.f;
#pragma unroll
    for (int e = 0; e < 2; e++) {
      const int h = 2 * hp + e, f = h == 0 ? 0 : h == 1 ? 3 : h == 2 ? 5 : 8;
      const uint32_t a0 = plo[h] & mfar, a2 = plo[h] & ~mfar, a3 = phi[h] & mfar, c1 = phi[h] & ~mfar;
      float sum[4] = {0.f, 0.f, 0.f, 0.f};
      mma1688(sum, plo[h], phi[h], 0x3F803F80u);
      const float r0 = rcp(sum[0]), r1 = rcp(sum[2]);
#pragma unroll
      for (int j = f; j < f + 2; j++) {
        float o[4] = {0.f, 0.f, 0.f, 0.f};
        mma16816(o, a0, 0u, a2, a3, vpv[j], vlo[j]);
        mma1688(o, 0u, c1, vhi[j]);
        ov[2 * j] = pack2(o[0] * r0, o[1] * r0);
        ov[2 * j + 1] = pack2(o[2] * r1, o[3] * r1);
      }
      const bool mine = e ? g >= 4 : g < 4;
      mma16816(sh, a0, 0u, a2, a3, mine ? vpv[hf] : 0u, mine ? vlo[hf] : 0u);
      mma1688(sh, 0u, c1, mine ? vhi[hf] : 0u);
      if (e == 0 || t >= 2) {
        i0 = r0;
        i1 = r1;
      }
    }
    ov[2 * hf] = pack2(sh[0] * i0, sh[1] * i0);
    ov[2 * hf + 1] = pack2(sh[2] * i1, sh[3] * i1);
  }
  TS(32 + 4 * par + w);
  mbar_wait(sb + OFF_BAR + 8 * B_P1, 0);
  const uint32_t oa = sb + OFF_OA + (lane >> 4) * 2048 + (32 * w + 2 * (lane & 15) + par) * 16;
#pragma unroll
  for (int j = 0; j < 5; j++) stsm4(oa + 4096 * j, ov + 4 * j);
  TSIF(par == 0 && w == 0, 120);
  fence_async_smem();
  TSIF(par == 0 && w == 0, 121);
  __syncwarp();
  if (lane == 0) mbar_arrive(sb + OFF_BAR + 8 * B_ATTN);
  TSM(w == 0 || w == 2, 122 + par + (w == 2 ? 3 : 0));
}

struct Maps {
  CUtensorMap x, wm, wt, k, v, y, wo, qm, qt, om, ot, yl, ol;
};

__device__ __forceinline__ void load_stage(uint32_t sb, int kb, int b, const Maps& m) {
  const uint32_t st = sb + (kb & 3) * STAGE_BYTES, bar = sb + OFF_BAR + 8 * (B_FULL1 + (kb & 3));
  const int r = b >> 3, hg = b & 7, slab = kb - KV_KB;
  const bool kv = slab >= 0 && slab < 5;
  const uint32_t kbar = sb + OFF_BAR + 8 * (B_KV + slab), dst = sb + OFF_KVS + slab * KVS_BYTES;
  mbar_expect_tx(bar, STAGE_BYTES);
  if (kv) mbar_expect_tx(kbar, KVS_BYTES);
  tma_3d(st, &m.x, 64 * kb, 64 * r, 0, bar);
  tma_3d(st + ST_W, &m.wm, 80 * hg + (tail_first(hg) ? 16 : 0), 64 * kb, 0, bar);
  tma_3d(st + ST_WT, &m.wt, 80 * hg + (tail_first(hg) ? 0 : 64), 64 * kb, 0, bar);
  if (kv) tma_3d(dst, &m.k, 0, 32 * (b >> 1) - 3, 2 * slab + (b & 1), kbar);
  if (kv) tma_3d(dst + KVS_V, &m.v, 0, 32 * (b >> 1), 2 * slab + (b & 1), kbar);
}

__global__ void __launch_bounds__(NTHR, 1) fused_kernel(const __grid_constant__ Maps m, const Params p) {
  extern __shared__ __align__(1024) uint8_t smem[];
  const uint32_t sb = (uint32_t)__cvta_generic_to_shared(smem);
  const uint32_t bars = sb + OFF_BAR;
  const int tid = threadIdx.x, lane = tid & 31;
  int b = blockIdx.x;
  b = (((b & 63) >> 3) * 2 + (b & 1)) * 8 + (((b < 64 ? 0x6521 : 0x7430) >> (4 * ((b >> 1) & 3))) & 7);
  const int r = b >> 3, hg = b & 7;

  if (tid == T_ISSUE) {
    TSM(true, 0);
    mbar_init(bars + 8 * B_F0, 1);
    fence_async_smem();
    mbar_expect_tx(bars + 8 * B_F0, ST_WT);
    tma_3d(sb, &m.x, 0, 64 * r, 0, bars + 8 * B_F0);
    tma_3d(sb + ST_W, &m.wm, 80 * hg + (tail_first(hg) ? 16 : 0), 0, 0, bars + 8 * B_F0);
#pragma unroll
    for (int i = 0; i < 4; i++) mbar_init(bars + 8 * (B_FULL1 + i), 1);
    fence_async_smem();
    mbar_expect_tx(bars + 8 * B_FULL1, STAGE_BYTES - ST_WT);
    tma_3d(sb + ST_WT, &m.wt, 80 * hg + (tail_first(hg) ? 0 : 64), 0, 0, bars + 8 * B_FULL1);
    load_stage(sb, 1, b, m);
  } else if (tid == T_INIT) {
#pragma unroll
    for (int i = 0; i < B_F0; i++) mbar_init(bars + 8 * i, i < B_GATE ? 8 : i < B_CVD ? 4 : i == B_CVD ? 20 : 1);
    fence_async_smem();
  }
  const int warp = __shfl_sync(0xffffffffu, tid >> 5, 0), wg = warp >> 2, w = warp & 3;
  __syncthreads();

  if (wg == 3) {
    asm volatile("setmaxnreg.dec.sync.aligned.u32 56;");
    if (w == 0) {
      if (lane == 0) {
#pragma unroll 1
        for (int kb = 2; kb < 10; kb++) {
          if (kb >= 4) mbar_wait(bars + 8 * (kb == 7 ? B_E3 : B_EMPTY1 + (kb & 3)), (kb >> 3) & 1);
          TSIF(kb >= 4, 44 + kb);
          load_stage(sb, kb, b, m);
          TSIF(kb == 3, 60);
          if (kb == TRIG_KB) mbar_arrive(bars + 8 * B_LAST);
        }
        mbar_wait(bars + 8 * B_WOP, 0);
        mbar_wait(bars + 8 * WL_TRIG, 0);
        mbar_wait(bars + 8 * B_EPOCH, 0);
        flag_wait(g_cnt + C_W + 32 * hg, (lds32(sb + OFF_EPOCH) + 1) * 16);
        TS(30);
#pragma unroll 1
        for (int j = 0; j < 8; j++) {
          if (j >= 6) mbar_wait(bars + 8 * (B_EMPTY2 + j - 6), 0);
          if (j == 4) mbar_wait(bars + 8 * (RB32 & 2 ? B_ORB : B_ATTN), 0);
          TSIF(j >= 6, 100 + j);
          mbar_expect_tx(bars + 8 * (B_FULL2 + j), j == 0 ? WO_BYTES : j == 5 ? O_BYTES + WO_BYTES + 512 : O_BYTES + WO_BYTES);
          bulk_load(sb + off_w(j), g_WO + (hg * 8 + step_src(hg, j)) * 800, WO_BYTES, bars + 8 * (B_FULL2 + j));
        }
        mbar_wait(bars + 8 * (B_EMPTY2 + 3), 0);
        mbar_expect_tx(bars + 8 * B_QF, O_BYTES);
        tma_2d(sb + OFF_QS, &m.qm, 80 * hg, 128 * r, bars + 8 * B_QF);
        tma_2d(sb + OFF_QT, &m.qt, 80 * hg + 64, 128 * r, bars + 8 * B_QF);
      }
    } else if (w == 1) {
      unsigned epoch = 0;
      if (lane == 0) {
        epoch = atomicAdd(g_cnt + C_LAUNCH, 1u) / NCTA;
        asm volatile("st.shared.u32 [%0], %1;" ::"r"(sb + OFF_EPOCH), "r"(epoch) : "memory");
        mbar_arrive(bars + 8 * B_EPOCH);
        mbar_wait(bars + 8 * B_KVD, 0);
        mbar_expect_tx(bars + 8 * B_HB, 5 * 4096);
#pragma unroll 1
        for (int c = 0; c < 5; c++) {
          if (c == 3) mbar_wait(bars + 8 * B_S3, 0);
          bulk_load(sb + off_ch(c) + U_BYTES, p.ssm_k + (5 * b + c) * SEQ, 4096, bars + 8 * B_HB);
        }
#pragma unroll
        for (int c = 0; c < 4; c++) mbar_expect_tx(bars + 8 * (B_U + c), c < 3 ? U_BYTES : 2 * U_BYTES);
        const uint4* usrc = g_U + 5 * b * U_PITCH;
        mbar_wait(bars + 8 * B_USIG, 0);
        flag_wait(g_cnt + C_PREP + 32 * (b & 15), (epoch + 1) * NCTA);
        TS(23);
#pragma unroll
        for (int c = 0; c < 5; c++) {
          if (c == 3) mbar_wait(bars + 8 * (B_U + 2), 0);
          bulk_load(sb + off_ch(c), usrc + c * U_PITCH, U_BYTES, bars + 8 * (B_U + (c < 3 ? c : 3)));
          TSIF(c == 0 || c == 4, 116 + (c >> 2));
        }
      }
      epoch = __shfl_sync(0xffffffffu, epoch, 0);
      if (lane < 8) {
        const int src = (b & ~7) | step_src(hg, lane);
        mbar_wait(bars + 8 * B_ATTN, 0);
        TS(20);
        bool seen = false;
#pragma unroll 1
        for (int spins = 0; spins < SPIN_LIMIT; spins++) {
          const bool now = !seen && (int)(flag_read(g_cnt + C_O + 32 * src) - (epoch + 1)) >= 0;
          if (now && lane >= 1 && lane < 4) bulk_load(sb + off_o(lane), g_O + src * 1280, O_BYTES, bars + 8 * (B_FULL2 + lane));
          seen = seen || now;
          if (__all_sync(0xff, seen)) break;
        }
        TS(21);
        if (lane == 5) bulk_load(sb + OFF_GATE, g_gate + 128 * r, 512, bars + 8 * (B_FULL2 + 5));
#pragma unroll 1
        for (int j = 4; j < 8; j++) {
          if (lane == j) {
            mbar_wait(bars + 8 * (j < 6 ? B_C34 : B_EMPTY2 + j - 6), 0);
            bulk_load(sb + off_o(j), g_O + src * 1280, O_BYTES, bars + 8 * (B_FULL2 + j));
          }
          __syncwarp(0xff);
        }
        TS(22);
      }
    } else if (w == 2) {
      mbar_wait(bars + 8 * B_PREP, 0);
      flag_signal(g_cnt + C_PREP, 16, lane);
      TS(25);
      if (lane == 0) {
        mbar_arrive(bars + 8 * B_USIG);
        mbar_expect_tx(bars + 8 * B_ORB, (RB32 & 2 ? O_BYTES / 4 : O_BYTES) + 64);
        mbar_wait(bars + 8 * B_GATE, 0);
        publish(g_gate + 16 * b, sb + OFF_GATE + 64 * hg, 64, bars + 8 * B_ORB);
        mbar_wait(bars + 8 * B_ATTN, 0);
        if (RB32 & 2) {
          bulk_store(g_O + b * 1280, sb + OFF_OA, O_BYTES);
          bulk_wait_read();
          tma_2d(sb + OFF_KVX + 10240, &m.ol, 48, b * 160, bars + 8 * B_ORB);
        } else {
          publish(g_O + b * 1280, sb + OFF_OA, O_BYTES, bars + 8 * B_ORB);
        }
        TS(74);
        mbar_wait(bars + 8 * B_ORB, 0);
        flag_bump(g_cnt + C_O + 32 * b);
        TS(26);
        mbar_arrive(bars + 8 * B_OSIG);
      }
    } else {
      if (lane == 0) {
        uint4* dst = g_WO + (hg * 8 + (r >> 1)) * 800 + (r & 1) * 80;
        mbar_wait(bars + 8 * B_S3, 0);
        asm volatile("cp.async.bulk.prefetch.L2.global [%0], 6400;" ::"l"(p.wo + b * 3200) : "memory");
        mbar_wait(bars + 8 * B_P1, 0);
        mbar_wait(bars + 8 * WB_TRIG, 0);
        mbar_expect_tx(bars + 8 * B_WST, WO_BYTES / 2);
        tma_3d(sb + OFF_WA, &m.wo, 0, 40 * r, 5 * hg, bars + 8 * B_WST);
        mbar_wait(bars + 8 * B_WST, 0);
#pragma unroll 1
        for (int n = 0; n < 5; n++) bulk_store(dst + 160 * n, sb + OFF_WA + 1280 * n, 1280);
        bulk_wait_read();
        mbar_expect_tx(bars + 8 * B_WST, WO_BYTES / 2);
#pragma unroll 1
        for (int n = 0; n < 5; n++) bulk_load(sb + OFF_WA + 1280 * n, dst + 160 * n, 1280, bars + 8 * B_WST);
        mbar_wait(bars + 8 * B_WST, 1);
        flag_bump(g_cnt + C_W + 32 * hg);
        mbar_arrive(bars + 8 * B_WOP);
        TS(71);
        mbar_expect_tx(bars + 8 * B_C34, 3 * (RB32 & 1 ? 1024 : U_BYTES));
        mbar_expect_tx(bars + 8 * B_YRB, 2 * (RB32 & 1 ? 1024 : U_BYTES));
#pragma unroll 1
        for (int c = 0; c < 5; c++) {
          mbar_wait(bars + 8 * (B_YST + c), 0);
          if (RB32 & 1) {
            bulk_store(g_U + (5 * b + c) * U_PITCH, sb + off_ch(c), U_BYTES);
            bulk_wait_read();
            tma_2d(sb + off_ch(c), &m.yl, 48, (5 * b + c) * (U_PITCH / 8), bars + 8 * (c < 3 ? B_C34 : B_YRB));
          } else {
            publish(g_U + (5 * b + c) * U_PITCH, sb + off_ch(c), U_BYTES, bars + 8 * (c < 3 ? B_C34 : B_YRB));
          }
        }
        TS(75);
        mbar_wait(bars + 8 * B_C34, 0);
        mbar_wait(bars + 8 * B_YRB, 0);
        flag_bump(g_cnt + C_Y + 32 * (b >> 4));
        TS(27);
        mbar_arrive(bars + 8 * B_YSIG);
        mbar_expect_tx(bars + 8 * B_YFULL, 20480);
        flag_wait(g_cnt + C_Y + 32 * hg, (lds32(sb + OFF_EPOCH) + 1) * 16);
        TS(24);
        tma_2d(sb + OFF_YT, &m.y, 128 * r, 80 * hg, bars + 8 * B_YFULL);
        tma_2d(sb + OFF_YT + 10240, &m.y, 128 * r + 64, 80 * hg, bars + 8 * B_YFULL);
      }
    }
  } else {
    asm volatile("setmaxnreg.inc.sync.aligned.u32 152;");
    if (wg < 2) {
      float acc[120];
#pragma unroll
      for (int i = 0; i < 120; i++) acc[i] = 0.f;
      const uint32_t da = desc_lo(sb + wg * 8192, 16), db = desc_lo(sb + ST_W, 8192), dc = desc_lo(sb + ST_WT, 2048);
      mbar_wait(bars + 8 * B_F0, 0);
      TSIF(w == 0 && wg == 0, 1);
      wg_fence();
#pragma unroll
      for (int k = 0; k < 4; k++) WgSST<192>::mma<HI_SW128, HI_SW128>(acc, da + 2 * k, db + 128 * k, 1);
      wg_commit();
      mbar_wait(bars + 8 * B_FULL1, 0);
      wg_fence();
#pragma unroll
      for (int k = 0; k < 4; k++) WgSST<48>::mma<HI_SW128, HI_SW32>(acc + 96, da + 2 * k, dc + 32 * k, 1);
      wg_commit();
#pragma unroll 1
      for (int kb = 1; kb < 10; kb++) {
        mbar_wait(bars + 8 * (B_FULL1 + (kb & 3)), (kb >> 2) & 1);
        const uint32_t so = (kb & 3) * (STAGE_BYTES >> 4);
        wg_fence();
#pragma unroll
        for (int k = 0; k < 4; k++) {
          WgSST<192>::mma<HI_SW128, HI_SW128>(acc, da + so + 2 * k, db + so + 128 * k, 1);
          WgSST<48>::mma<HI_SW128, HI_SW32>(acc + 96, da + so + 2 * k, dc + so + 32 * k, 1);
        }
        wg_commit();
        wg_wait<1>();
        if (lane == 0) mbar_arrive(bars + 8 * (kb == 4 ? B_E3 : B_EMPTY1 + ((kb - 1) & 3)));
      }
      mbar_wait(bars + 8 * B_EPOCH, 0);
      const uint32_t tag = lds32(sb + OFF_EPOCH) + 1;
      mbar_wait(bars + 8 * B_S3, 0);
      wg_wait<0>();
      pin<120>(acc);
      if (lane == 0) mbar_arrive(bars + 8 * B_P1);
      TSM(w == 0, 3 + wg);
      attention(acc, sb, b, wg, w, lane, tag);
    } else {
      const int tw = tid & 127, chl = 64 * (b & 1) + 8 * w + (lane >> 2);
      uint4* up = g_U + chl * U_PITCH + ((4 * (b >> 1) + (lane & 3)) ^ ((b >> 2) & 1));
      uint2 sw[10];
      uint32_t dv = 0;
      if (lane < 5) dv = __ldg(reinterpret_cast<const unsigned short*>(p.ssm_D) + 5 * b + lane);
#pragma unroll
      for (int i = 0; i < 10; i++) sw[i] = ldg64(reinterpret_cast<const uint2*>(p.shift_k) + chl + 128 * (i >> 1) + 32 * (i & 1));
      uint32_t tab[12];
      uint32_t tt[2];
      fft_tables(tab, tw);
      fft_twiddles(tt, tw);
      uint4 res[10];
#pragma unroll
      for (int i = 0; i < 10; i++) res[i] = make_uint4(0, 0, 0, 0);
#pragma unroll 1
      for (int slab = 0; slab < 5; slab++) {
#pragma unroll
        for (int i = 0; i < 8; i++) res[i] = res[i + 2];
        prep_slab(res + 8, sw, sb, slab, w, lane);
        TSIF(w == 0, 99 + 4 * slab);
#pragma unroll
        for (int i = 0; i < 8; i++) sw[i] = sw[i + 2];
      }
      TSIF(w == 0, 28);
      __syncwarp();
      if (lane == 0) mbar_arrive(bars + 8 * B_KVD + ((res[8].x ^ res[9].x) & p.zero));
      mbar_wait(bars + 8 * B_KVD, 0);
      fft_tables_store(tab, sb, tw);
      mbar_wait(bars + 8 * B_LAST, 0);
#pragma unroll
      for (int i = 0; i < 10; i++) up[(128 * (i >> 1) + 32 * (i & 1)) * U_PITCH] = res[i];
      __syncwarp();
      if (lane == 0) mbar_arrive(bars + 8 * B_PREP);
      TSIF(w == 0, 5);
      mbar_wait(bars + 8 * B_LAST, 0);
      prep_gate(p, sb, b, w, lane);
      __syncwarp();
      if (lane == 0) mbar_arrive(bars + 8 * B_GATE);
      TSIF(w == 0, 72);
      mbar_wait(bars + 8 * B_HB, 0);
      TSIF(w == 0, 2);
      const uint32_t ha = sb + U_BYTES + ((tw >> 3) * 16 + 8 + (tw & 7)) * 16;
      uint4 hv[5];
#pragma unroll
      for (int c = 0; c < 5; c++) hv[c] = lds128(ha + off_ch(c));
      __syncwarp();
#pragma unroll
      for (int c = 0; c < 5; c++) sts128((ha ^ 16) + off_ch(c), hv[c].x, hv[c].y, hv[c].z, hv[c].w);
      asm volatile("st.shared.v2.u32 [%0], {%1, %2};" ::"r"(sb + OFF_TT + 8 * tw), "r"(tt[0]), "r"(tt[1]) : "memory");
      if (tw < 5) asm volatile("st.shared.f32 [%0], %1;" ::"r"(sb + OFF_D + 4 * tw), "f"(bf_lo(dv) * 0.125f) : "memory");
      fence_async_smem();
      __syncwarp();
      if (lane == 0) mbar_arrive(bars + 8 * B_HA);
      TSIF(w == 0, 6);
    }

    FftConst fc;
    TSM(w == 0 && wg == 0, 104);
    mbar_wait(bars + 8 * B_HA, 0);
    fft_matrices(fc, sb, w, lane);
    TSM(w == 0 && wg == 0, 105);
    TSM(w == 0 && wg == 2, 124);
#pragma unroll 1
    for (uint32_t tasks = wg == 0 ? TASK0 : wg == 1 ? TASK1 : TASK2; tasks; tasks >>= 4) {
      const int c = (tasks & 7) - 1;
      conv_channel(fc, sb, c, wg, w, lane);
      if (lane == 0) mbar_arrive(bars + 8 * (B_YST + c));
      TSM(w == 0, 10 + c);
    }

    if (wg != WO_SKIP) {
      const int wg = (warp >> 2) > WO_SKIP ? (warp >> 2) - 1 : warp >> 2;
      const int g = lane >> 2;
      float acc[40];
#pragma unroll
      for (int i = 0; i < 40; i++) acc[i] = 0.f;
      const uint32_t da = desc_lo(sb + wg * 1024, 2048), db = desc_lo(sb, 2560);
      mbar_wait(bars + 8 * B_ORB, 0);
      mbar_wait(bars + 8 * B_FULL2, 0);
      mbar_wait(bars + 8 * B_CVD, 0);
      TSM(w == 0, 15 + wg);
#pragma unroll 1
      for (int j = 0; j < 8; j++) {
        mbar_wait(bars + 8 * (B_FULL2 + j), 0);
        TSM(w == 0 && wg == 0, 44 + (j < 4 ? j : j + 6));
        const uint32_t oa = da + (off_o(j) >> 4), ob = db + (off_w(j) >> 4);
        wg_fence();
#pragma unroll
        for (int k = 0; k < 5; k++) WgSST<80>::mma<HI_NONE, HI_SW32>(acc, oa + 256 * k, ob + 32 * k, 1);
        wg_commit();
        wg_wait<1>();
        if (j >= 1 && j <= 4 && lane == 0) mbar_arrive(bars + 8 * (B_EMPTY2 + j - 1));
      }
      TSIF(w == 0 && wg == 0, 113);
      const int tr = 64 * wg + 16 * w + (lane & 15);
      const uint32_t fm = sb + OFF_QS + tr * 128, fx = (lane >> 4) ^ (tr & 7);
      const uint32_t ft = sb + OFF_QT + tr * 32 + (((lane >> 4) ^ (tr >> 2)) & 1) * 16;
      const float g0 = __uint_as_float(lds32(sb + OFF_GATE + (64 * wg + 16 * w + g) * 4));
      const float g1 = __uint_as_float(lds32(sb + OFF_GATE + (64 * wg + 16 * w + 8 + g) * 4));
      const uint32_t ga = pack2(g0, g0), gb = pack2(g1, g1);
      const uint32_t na = pack2(1.f - g0, 1.f - g0), nb = pack2(1.f - g1, 1.f - g1);

      uint32_t qf[20];
      mbar_wait(bars + 8 * B_QF, 0);
      TSM(w == 0 && wg == 0, 99);
#pragma unroll
      for (int j = 0; j < 5; j++) ldsm4(qf + 4 * j, j < 4 ? fm + ((fx ^ (2 * j)) << 4) : ft);
#pragma unroll
      for (int i = 0; i < 20; i++) {
        qf[i] = bmul((i & 1) ? gb : ga, qf[i]);
        asm volatile("" : "+r"(qf[i]));
      }

      wg_wait<0>();
      pin<40>(acc);
      TSM(w == 0, 17 + wg);
      uint32_t pb[20];
#pragma unroll
      for (int j = 0; j < 10; j++) {
        pb[2 * j] = bmul(na, pack2(acc[4 * j], acc[4 * j + 1]));
        pb[2 * j + 1] = bmul(nb, pack2(acc[4 * j + 2], acc[4 * j + 3]));
        asm volatile("" : "+r"(pb[2 * j]), "+r"(pb[2 * j + 1]));
      }
      const uint32_t ya = sb + OFF_YT + wg * 10240 + ((lane >> 4) * 8 + (lane & 7)) * 128 +
                          (((2 * w + (((lane >> 3) & 1) ^ wg)) ^ (lane & 7)) << 4);
      mbar_wait(bars + 8 * B_YFULL, 0);
      TSM(w == 0 && wg == 0, 19);
#pragma unroll
      for (int j = 0; j < 5; j++) {
        uint32_t y[4];
        ldsm4t(y, ya + 2048 * j);
#pragma unroll
        for (int i = 0; i < 4; i++)
          qf[4 * j + i] = bfma(qf[4 * j + i], y[i], pb[4 * j + i]);
      }
#pragma unroll
      for (int j = 0; j < 5; j++) stsm4(j < 4 ? fm + ((fx ^ (2 * j)) << 4) : ft, qf + 4 * j);
      fence_async_smem();
      __syncwarp();
      if (lane == 0) {
        const int row = 64 * wg + 16 * w;
        asm volatile("cp.async.bulk.tensor.2d.global.shared::cta.bulk_group [%0, {%2, %3}], [%1];"
                     ::"l"(&m.om), "r"(sb + OFF_QS + row * 128), "r"(80 * hg), "r"(128 * r + row) : "memory");
        asm volatile("cp.async.bulk.tensor.2d.global.shared::cta.bulk_group [%0, {%2, %3}], [%1];"
                     ::"l"(&m.ot), "r"(sb + OFF_QT + row * 32), "r"(80 * hg + 64), "r"(128 * r + row) : "memory");
        asm volatile("cp.async.bulk.commit_group;\ncp.async.bulk.wait_group.read 0;" ::: "memory");
      }
      TSM(w == 0 || w == 3, 40 + 2 * wg + (w & 1));
    }
  }
}

typedef CUresult (*EncodeFn)(CUtensorMap*, CUtensorMapDataType, cuuint32_t, void*, const cuuint64_t*, const cuuint64_t*,
                             const cuuint32_t*, const cuuint32_t*, CUtensorMapInterleave, CUtensorMapSwizzle,
                             CUtensorMapL2promotion, CUtensorMapFloatOOBfill);

void encode(EncodeFn fn, CUtensorMap* tm, const void* base, int rank, const cuuint64_t* dims, const cuuint64_t* strides,
            const cuuint32_t* box, CUtensorMapSwizzle swz) {
  const cuuint32_t ones[3] = {1, 1, 1};
  fn(tm, CU_TENSOR_MAP_DATA_TYPE_BFLOAT16, rank, const_cast<void*>(base), dims, strides, box, ones,
     CU_TENSOR_MAP_INTERLEAVE_NONE, swz, CU_TENSOR_MAP_L2_PROMOTION_L2_128B, CU_TENSOR_MAP_FLOAT_OOB_FILL_NONE);
}

}

extern "C" void kernel_launch(void* const* d_in, const int* in_sizes, int n_in, void* d_out, int out_size) {
  (void)in_sizes; (void)n_in; (void)out_size;
  Params p;
  p.q = (const __nv_bfloat16*)d_in[0];
  p.k = (const __nv_bfloat16*)d_in[1];
  p.v = (const __nv_bfloat16*)d_in[2];
  p.shift_k = (const __nv_bfloat16*)d_in[3];
  p.ssm_k = (const __nv_bfloat16*)d_in[4];
  p.ssm_D = (const __nv_bfloat16*)d_in[5];
  p.wqkv = (const __nv_bfloat16*)d_in[7];
  p.wo = (const __nv_bfloat16*)d_in[8];
  p.gate_w = (const __nv_bfloat16*)d_in[9];
  p.out = (__nv_bfloat16*)d_out;
  p.zero = 0;

  static EncodeFn fn = nullptr;
  static void *yaddr = nullptr, *oaddr = nullptr;
  if (!fn) {
    cudaDriverEntryPointQueryResult qr;
    void* f = nullptr;
    cudaGetDriverEntryPoint("cuTensorMapEncodeTiled", &f, cudaEnableDefault, &qr);
    fn = (EncodeFn)f;
    cudaGetSymbolAddress(&yaddr, g_U);
    cudaGetSymbolAddress(&oaddr, g_O);
    cudaFuncSetAttribute(fused_kernel, cudaFuncAttributeMaxDynamicSharedMemorySize, SMEM_BYTES);
  }
  Maps m;
  {
    const cuuint64_t dims[3] = {640, 1024, 2}, st[2] = {2560, 1280};
    const cuuint32_t box[3] = {64, 64, 2};
    encode(fn, &m.x, p.q, 3, dims, st, box, CU_TENSOR_MAP_SWIZZLE_128B);
  }
  {
    const cuuint64_t dims[3] = {640, 640, 3}, st[2] = {3840, 1280};
    const cuuint32_t box[3] = {64, 64, 3}, boxt[3] = {16, 64, 3};
    encode(fn, &m.wm, p.wqkv, 3, dims, st, box, CU_TENSOR_MAP_SWIZZLE_128B);
    encode(fn, &m.wt, p.wqkv, 3, dims, st, boxt, CU_TENSOR_MAP_SWIZZLE_32B);
  }
  {
    const cuuint64_t dims[3] = {64, 2048, 10}, st[2] = {1280, 128};
    const cuuint32_t boxk[3] = {64, 35, 1}, boxv[3] = {64, 32, 1};
    encode(fn, &m.k, p.k, 3, dims, st, boxk, CU_TENSOR_MAP_SWIZZLE_128B);
    encode(fn, &m.v, p.v, 3, dims, st, boxv, CU_TENSOR_MAP_SWIZZLE_128B);
  }
  {
    const cuuint64_t dims[3] = {16, 640, 40}, st[2] = {1280, 32};
    const cuuint32_t box[3] = {16, 40, 5};
    encode(fn, &m.wo, p.wo, 3, dims, st, box, CU_TENSOR_MAP_SWIZZLE_32B);
  }
  {
    const cuuint64_t dims[2] = {2048, 640}, st[1] = {U_PITCH * 16};
    const cuuint32_t box[2] = {64, 80};
    encode(fn, &m.y, yaddr, 2, dims, st, box, CU_TENSOR_MAP_SWIZZLE_128B);
    const cuuint64_t dl[2] = {64, DIM * U_PITCH / 8}, dol[2] = {64, NCTA * 160}, sl[1] = {128};
    const cuuint32_t bl[2] = {16, 32}, bol[2] = {16, 160};
    encode(fn, &m.yl, yaddr, 2, dl, sl, bl, CU_TENSOR_MAP_SWIZZLE_NONE);
    encode(fn, &m.ol, oaddr, 2, dol, sl, bol, CU_TENSOR_MAP_SWIZZLE_NONE);
  }
  {
    const cuuint64_t dims[2] = {640, 2048}, st[1] = {1280};
    const cuuint32_t bqm[2] = {64, 128}, bqt[2] = {16, 128}, bom[2] = {64, 16}, bot[2] = {16, 16};
    encode(fn, &m.qm, p.q, 2, dims, st, bqm, CU_TENSOR_MAP_SWIZZLE_128B);
    encode(fn, &m.qt, p.q, 2, dims, st, bqt, CU_TENSOR_MAP_SWIZZLE_32B);
    encode(fn, &m.om, p.out, 2, dims, st, bom, CU_TENSOR_MAP_SWIZZLE_128B);
    encode(fn, &m.ot, p.out, 2, dims, st, bot, CU_TENSOR_MAP_SWIZZLE_32B);
  }
  fused_kernel<<<NCTA, NTHR, SMEM_BYTES>>>(m, p);
}
```

```cpp
#include <cuda.h>
#include <cuda_bf16.h>
#include <cuda_runtime.h>
#include <stdint.h>

namespace {

constexpr int SEQ = 2048, DIM = 640, NCTA = 128, NTHR = 512;

#define TRIG_KB 9
#define KV_KB 2
#define DEV_EXIT 0
#define FENCE_LO 0
#define FENCE_HI 0
#define WB_TRIG B_USIG
#define T_ISSUE 256
#define RB32 3
#define WO_SKIP 1
#define T_INIT 448
#define TASK0 0x3
#define TASK1 0x52
#define TASK2 0x41
#define WL_TRIG B_WOP

constexpr uint32_t STAGE_BYTES = 47104, ST_W = 16384, ST_WT = 40960;
constexpr uint32_t O_BYTES = 20480, WO_BYTES = 12800;
constexpr uint32_t OFF_OA = 0;
constexpr uint32_t OFF_QS = 3 * O_BYTES, OFF_QT = OFF_QS + 16384;
constexpr uint32_t OFF_WC = 81920;
constexpr uint32_t OFF_WA = 94720;
constexpr uint32_t OFF_GATE = 145920;
constexpr uint32_t OFF_TT = 146432;
constexpr uint32_t OFF_KVX = 148480;
constexpr uint32_t OFF_CH3 = 163840;
constexpr uint32_t CH_BYTES = 12288, U_BYTES = 4096;
constexpr uint32_t OFF_FT = 225280, OFF_GT = 229376;
constexpr uint32_t OFF_CH0 = 188416;
constexpr uint32_t OFF_KVS = OFF_CH0, KVS_V = 4480, KVS_BYTES = 8576;
constexpr uint32_t OFF_YT = 163840;
constexpr uint32_t OFF_BAR = 231936;
constexpr uint32_t SMEM_BYTES = OFF_BAR + 512;

enum : uint32_t {
  B_EMPTY1 = 0, B_S3 = 3, B_E3 = 4, B_EMPTY2 = 5, B_ATTN = 9, B_P1 = 10,
  B_GATE = 11, B_HA = 12, B_KVD = 13, B_PREP = 14, B_YST = 15,
  B_CVD = 20,
  B_FULL2 = 21, B_U = 29, B_KV = 33, B_HB = 38, B_C34 = 39, B_YRB = 40, B_YFULL = 41, B_EPOCH = 42, B_LAST = 43, B_OSIG = 44,
  B_WOP = 45, B_USIG = 46, B_WST = 47, B_QF = 48, B_ORB = 49, B_YSIG = 50,
  B_F0 = 51, B_FULL1 = 52
};
constexpr uint32_t OFF_EPOCH = OFF_BAR + 8 * 58, OFF_D = OFF_BAR + 8 * 60;
__device__ __forceinline__ uint32_t off_o(int j) { return j < 4 ? OFF_OA + j * O_BYTES : j < 6 ? OFF_CH0 + (j - 4) * O_BYTES : OFF_OA + (j - 6) * O_BYTES; }
__device__ __forceinline__ uint32_t off_w(int j) { return j < 4 ? OFF_WA + j * WO_BYTES : j == 4 ? OFF_KVX : j == 5 ? OFF_WC : OFF_WA + (j - 6) * WO_BYTES; }
__device__ __forceinline__ int step_src(int hg, int j) { return j == 0 ? hg : j <= hg ? j - 1 : j; }
__device__ __forceinline__ bool tail_first(int hg) { return (hg & 3) == 3; }
__device__ __forceinline__ uint32_t off_ch(int c) { return (c < 3 ? OFF_CH0 : OFF_CH3 - 3 * CH_BYTES) + c * CH_BYTES; }

#define U_PITCH 264
__device__ __align__(1024) uint4 g_U[DIM * U_PITCH];
__device__ __align__(128) uint4 g_O[NCTA * 1280];
__device__ uint4 g_WO[64 * 800];
__device__ uint4 g_halo[NCTA * 2 * 7 * 32];
__device__ __align__(128) float g_gate[SEQ];
__device__ unsigned g_cnt[32 * (1 + 2 * 16 + 8 + NCTA)];
constexpr int C_LAUNCH = 0, C_PREP = 32, C_Y = 32 * 17, C_W = 32 * 33, C_O = 32 * 41;

#define TSM(cond, slot) do { } while (0)
#define TSIF(cond, slot) do { if (__LINE__ >= FENCE_LO && __LINE__ < FENCE_HI) sched_fence(); } while (0)
__device__ __forceinline__ void sched_fence() {
  asm volatile("{\n.reg .pred p;\n.reg .u32 c;\nmov.u32 c, %%clock;\nsetp.eq.u32 p, c, 0;\n@p st.shared.u32 [%0], c;\n}"
               ::"r"(1024 + OFF_EPOCH + 4) : "memory");
}
#define TS(slot) TSIF(true, slot)

struct Params {
  const __nv_bfloat16 *q, *k, *v, *shift_k, *ssm_k, *ssm_D, *wqkv, *wo, *gate_w;
  __nv_bfloat16* out;
  uint32_t zero;
};

constexpr int SPIN_LIMIT = 1 << 17;

__device__ __forceinline__ void mbar_init(uint32_t bar, uint32_t count) {
  asm volatile("mbarrier.init.shared::cta.b64 [%0], %1;" ::"r"(bar), "r"(count) : "memory");
}
__device__ __forceinline__ void mbar_expect_tx(uint32_t bar, uint32_t bytes) {
  asm volatile("mbarrier.arrive.expect_tx.shared::cta.b64 _, [%0], %1;" ::"r"(bar), "r"(bytes) : "memory");
}
__device__ __forceinline__ void mbar_arrive(uint32_t bar) {
  asm volatile("mbarrier.arrive.shared::cta.b64 _, [%0];" ::"r"(bar) : "memory");
}
__device__ __forceinline__ void mbar_wait(uint32_t bar, uint32_t parity) {
  uint32_t ok;
  int spins = 0;
  do {
      asm volatile("{\n.reg .pred p;\nmbarrier.try_wait.parity.shared::cta.b64 p, [%1], %2;\nselp.b32 %0, 1, 0, p;\n}"
                   : "=r"(ok) : "r"(bar), "r"(parity) : "memory");
    if (++spins > SPIN_LIMIT) break;
  } while (!ok);
}
__device__ __forceinline__ unsigned flag_read(const unsigned* p) {
  unsigned v;
  asm volatile("ld.relaxed.gpu.global.u32 %0, [%1];" : "=r"(v) : "l"(p) : "memory");
  return v;
}
__device__ __forceinline__ void flag_poll(const unsigned* p, unsigned target) {
  unsigned v;
  int spins = 0;
  do {
    asm volatile("ld.relaxed.gpu.global.u32 %0, [%1];" : "=r"(v) : "l"(p) : "memory");
    if (++spins > SPIN_LIMIT) break;
  } while ((int)(v - target) < 0);
}
__device__ __forceinline__ void flag_wait(const unsigned* p, unsigned target) {
  flag_poll(p, target);
}
__device__ __forceinline__ void flag_signal(unsigned* p, int n, int lane) {
  if (lane == 0) asm volatile("fence.release.gpu;" ::: "memory");
  __syncwarp();
  if (lane < n) asm volatile("red.relaxed.gpu.global.add.u32 [%0], 1;" ::"l"(p + 32 * lane) : "memory");
}
__device__ __forceinline__ void flag_bump(unsigned* p) {
  asm volatile("red.relaxed.gpu.global.add.u32 [%0], 1;" ::"l"(p) : "memory");
}
__device__ __forceinline__ void fence_async_smem() { asm volatile("fence.proxy.async.shared::cta;" ::: "memory"); }
__device__ __forceinline__ void wg_sync(int id) { asm volatile("bar.sync %0, 128;" ::"r"(id) : "memory"); }

__device__ __forceinline__ void tma_2d(uint32_t dst, const CUtensorMap* tm, int c0, int c1, uint32_t bar) {
  asm volatile("cp.async.bulk.tensor.2d.shared::cluster.global.mbarrier::complete_tx::bytes [%0], [%1, {%3, %4}], [%2];"
               ::"r"(dst), "l"(tm), "r"(bar), "r"(c0), "r"(c1) : "memory");
}
__device__ __forceinline__ void tma_3d(uint32_t dst, const CUtensorMap* tm, int c0, int c1, int c2, uint32_t bar) {
  asm volatile("cp.async.bulk.tensor.3d.shared::cluster.global.mbarrier::complete_tx::bytes [%0], [%1, {%3, %4, %5}], [%2];"
               ::"r"(dst), "l"(tm), "r"(bar), "r"(c0), "r"(c1), "r"(c2) : "memory");
}
__device__ __forceinline__ void bulk_load(uint32_t dst, const void* src, uint32_t bytes, uint32_t bar) {
  asm volatile("cp.async.bulk.shared::cluster.global.mbarrier::complete_tx::bytes [%0], [%1], %2, [%3];"
               ::"r"(dst), "l"(src), "r"(bytes), "r"(bar) : "memory");
}
__device__ __forceinline__ void bulk_store(void* dst, uint32_t src, uint32_t bytes) {
  asm volatile("cp.async.bulk.global.shared::cta.bulk_group [%0], [%1], %2;" ::"l"(dst), "r"(src), "r"(bytes) : "memory");
}
__device__ __forceinline__ void bulk_wait_read() {
  asm volatile("cp.async.bulk.commit_group;\ncp.async.bulk.wait_group.read 0;" ::: "memory");
}

__device__ __forceinline__ void publish(void* dst, uint32_t src, uint32_t bytes, uint32_t bar) {
  bulk_store(dst, src, bytes);
  bulk_wait_read();
  bulk_load(src, dst, bytes, bar);
}

__device__ __forceinline__ void wg_fence() { asm volatile("wgmma.fence.sync.aligned;" ::: "memory"); }
__device__ __forceinline__ void wg_commit() { asm volatile("wgmma.commit_group.sync.aligned;" ::: "memory"); }
template <int N> __device__ __forceinline__ void wg_wait() { asm volatile("wgmma.wait_group.sync.aligned %0;" ::"n"(N) : "memory"); }
__device__ __forceinline__ uint32_t desc_lo(uint32_t addr, uint32_t lbo) { return ((addr & 0x3FFFF) >> 4) | ((lbo >> 4) << 16); }
constexpr uint32_t desc_hi(uint32_t sbo, uint32_t swz) { return (sbo >> 4) | (swz << 30); }
constexpr uint32_t HI_SW128 = desc_hi(1024, 1), HI_SW64 = desc_hi(512, 2), HI_SW32 = desc_hi(256, 3), HI_NONE = desc_hi(128, 0);
template <int N> __device__ __forceinline__ void pin(float* d) {
#pragma unroll
  for (int i = 0; i < N; i++) asm volatile("" : "+f"(d[i])::"memory");
}

__device__ __forceinline__ uint32_t lds32(uint32_t a) {
  uint32_t v;
  asm volatile("ld.volatile.shared.u32 %0, [%1];" : "=r"(v) : "r"(a) : "memory");
  return v;
}
__device__ __forceinline__ uint2 ldg64(const void* a) {
  uint2 v;
  asm volatile("ld.global.nc.v2.u32 {%0, %1}, [%2];" : "=r"(v.x), "=r"(v.y) : "l"(a) : "memory");
  return v;
}
__device__ __forceinline__ void ldsm4(uint32_t* r, uint32_t a) {
  asm volatile("ldmatrix.sync.aligned.m8n8.x4.shared.b16 {%0, %1, %2, %3}, [%4];"
               : "=r"(r[0]), "=r"(r[1]), "=r"(r[2]), "=r"(r[3]) : "r"(a) : "memory");
}
__device__ __forceinline__ void ldsm4t(uint32_t* r, uint32_t a) {
  asm volatile("ldmatrix.sync.aligned.m8n8.x4.trans.shared.b16 {%0, %1, %2, %3}, [%4];"
               : "=r"(r[0]), "=r"(r[1]), "=r"(r[2]), "=r"(r[3]) : "r"(a) : "memory");
}
__device__ __forceinline__ uint2 lds64(uint32_t a) {
  uint2 v;
  asm volatile("ld.shared.v2.u32 {%0, %1}, [%2];" : "=r"(v.x), "=r"(v.y) : "r"(a) : "memory");
  return v;
}
__device__ __forceinline__ uint4 lds128(uint32_t a) {
  uint4 v;
  asm volatile("ld.shared.v4.u32 {%0, %1, %2, %3}, [%4];" : "=r"(v.x), "=r"(v.y), "=r"(v.z), "=r"(v.w) : "r"(a) : "memory");
  return v;
}
__device__ __forceinline__ void sts128(uint32_t a, uint32_t x, uint32_t y, uint32_t z, uint32_t w) {
  asm volatile("st.shared.v4.u32 [%0], {%1, %2, %3, %4};" ::"r"(a), "r"(x), "r"(y), "r"(z), "r"(w) : "memory");
}
__device__ __forceinline__ void stsm4(uint32_t a, const uint32_t* r) {
  asm volatile("stmatrix.sync.aligned.m8n8.x4.shared.b16 [%0], {%1, %2, %3, %4};" ::"r"(a), "r"(r[0]), "r"(r[1]), "r"(r[2]), "r"(r[3]) : "memory");
}
__device__ __forceinline__ uint32_t pack2(float lo, float hi) {
  uint32_t r;
  asm("cvt.rn.bf16x2.f32 %0, %1, %2;" : "=r"(r) : "f"(hi), "f"(lo));
  return r;
}
__device__ __forceinline__ uint32_t movm(uint32_t a) {
  uint32_t d;
  asm volatile("movmatrix.sync.aligned.m8n8.trans.b16 %0, %1;" : "=r"(d) : "r"(a));
  return d;
}
__device__ __forceinline__ uint32_t bmul(uint32_t a, uint32_t b) {
  uint32_t d;
  asm("mul.rn.bf16x2 %0, %1, %2;" : "=r"(d) : "r"(a), "r"(b));
  return d;
}
__device__ __forceinline__ uint32_t badd(uint32_t a, uint32_t b) {
  uint32_t d;
  asm("add.rn.bf16x2 %0, %1, %2;" : "=r"(d) : "r"(a), "r"(b));
  return d;
}
__device__ __forceinline__ uint32_t bfma(uint32_t a, uint32_t b, uint32_t c) {
  uint32_t d;
  asm("fma.rn.bf16x2 %0, %1, %2, %3;" : "=r"(d) : "r"(a), "r"(b), "r"(c));
  return d;
}
__device__ __forceinline__ float bf_lo(uint32_t x) { return __uint_as_float(x << 16); }
__device__ __forceinline__ float bf_hi(uint32_t x) { return __uint_as_float(x & 0xFFFF0000u); }
__device__ __forceinline__ float ex2(float x) {
  float y;
  asm("ex2.approx.ftz.f32 %0, %1;" : "=f"(y) : "f"(x));
  return y;
}
__device__ __forceinline__ float rcp(float x) {
  float y;
  asm("rcp.approx.ftz.f32 %0, %1;" : "=f"(y) : "f"(x));
  return y;
}
__device__ __forceinline__ void mma16816(float* d, uint32_t a0, uint32_t a1, uint32_t a2, uint32_t a3, uint32_t b0, uint32_t b1) {
  asm volatile("mma.sync.aligned.m16n8k16.row.col.f32.bf16.bf16.f32 {%0, %1, %2, %3}, {%4, %5, %6, %7}, {%8, %9}, {%0, %1, %2, %3};"
               : "+f"(d[0]), "+f"(d[1]), "+f"(d[2]), "+f"(d[3])
               : "r"(a0), "r"(a1), "r"(a2), "r"(a3), "r"(b0), "r"(b1));
}
__device__ __forceinline__ void mma1688(float* d, uint32_t a0, uint32_t a1, uint32_t b0) {
  asm volatile("mma.sync.aligned.m16n8k8.row.col.f32.bf16.bf16.f32 {%0, %1, %2, %3}, {%4, %5}, {%6}, {%0, %1, %2, %3};"
               : "+f"(d[0]), "+f"(d[1]), "+f"(d[2]), "+f"(d[3])
               : "r"(a0), "r"(a1), "r"(b0));
}

template <int N> struct WgRS;
template <int N> struct WgSST;
template <> struct WgRS<32> {
  template <uint32_t HB>
  static __device__ __forceinline__ void mma(float* d, const uint32_t* a, uint32_t db) {
    asm volatile("{\n.reg .pred p;\n.reg .b64 db;\nsetp.ne.b32 p, %22, 0;\n"
      "mov.b64 db, {%20, %21};\n"
      "wgmma.mma_async.sync.aligned.m64n32k16.f32.bf16.bf16 {"
      "%0, %1, %2, %3, %4, %5, %6, %7, %8, %9, %10, %11, %12, %13, %14, %15"
      "}, {%16, %17, %18, %19}, db, p, 1, 1, 1;\n}\n"
      : "+f"(d[0]), "+f"(d[1]), "+f"(d[2]), "+f"(d[3]), "+f"(d[4]), "+f"(d[5]), "+f"(d[6]), "+f"(d[7]),
        "+f"(d[8]), "+f"(d[9]), "+f"(d[10]), "+f"(d[11]), "+f"(d[12]), "+f"(d[13]), "+f"(d[14]), "+f"(d[15])
      : "r"(a[0]), "r"(a[1]), "r"(a[2]), "r"(a[3]), "r"(db), "n"(HB), "n"(1));
  }
  template <uint32_t HB>
  static __device__ __forceinline__ void set(float* d, const uint32_t* a, uint32_t db) {
    asm volatile("{\n.reg .pred p;\n.reg .b64 db;\nsetp.ne.b32 p, %22, 0;\n"
      "mov.b64 db, {%20, %21};\n"
      "wgmma.mma_async.sync.aligned.m64n32k16.f32.bf16.bf16 {"
      "%0, %1, %2, %3, %4, %5, %6, %7, %8, %9, %10, %11, %12, %13, %14, %15"
      "}, {%16, %17, %18, %19}, db, p, 1, 1, 1;\n}\n"
      : "=f"(d[0]), "=f"(d[1]), "=f"(d[2]), "=f"(d[3]), "=f"(d[4]), "=f"(d[5]), "=f"(d[6]), "=f"(d[7]),
        "=f"(d[8]), "=f"(d[9]), "=f"(d[10]), "=f"(d[11]), "=f"(d[12]), "=f"(d[13]), "=f"(d[14]), "=f"(d[15])
      : "r"(a[0]), "r"(a[1]), "r"(a[2]), "r"(a[3]), "r"(db), "n"(HB), "n"(0));
  }
};
template <> struct WgRS<64> {
  template <uint32_t HB>
  static __device__ __forceinline__ void mma(float* d, const uint32_t* a, uint32_t db) {
    asm volatile("{\n.reg .pred p;\n.reg .b64 db;\nsetp.ne.b32 p, %38, 0;\n"
      "mov.b64 db, {%36, %37};\n"
      "wgmma.mma_async.sync.aligned.m64n64k16.f32.bf16.bf16 {"
      "%0, %1, %2, %3, %4, %5, %6, %7, %8, %9, %10, %11, %12, %13, %14, %15, "
      "%16, %17, %18, %19, %20, %21, %22, %23, %24, %25, %26, %27, %28, %29, %30, %31"
      "}, {%32, %33, %34, %35}, db, p, 1, 1, 1;\n}\n"
      : "+f"(d[0]), "+f"(d[1]), "+f"(d[2]), "+f"(d[3]), "+f"(d[4]), "+f"(d[5]), "+f"(d[6]), "+f"(d[7]),
        "+f"(d[8]), "+f"(d[9]), "+f"(d[10]), "+f"(d[11]), "+f"(d[12]), "+f"(d[13]), "+f"(d[14]), "+f"(d[15]),
        "+f"(d[16]), "+f"(d[17]), "+f"(d[18]), "+f"(d[19]), "+f"(d[20]), "+f"(d[21]), "+f"(d[22]), "+f"(d[23]),
        "+f"(d[24]), "+f"(d[25]), "+f"(d[26]), "+f"(d[27]), "+f"(d[28]), "+f"(d[29]), "+f"(d[30]), "+f"(d[31])
      : "r"(a[0]), "r"(a[1]), "r"(a[2]), "r"(a[3]), "r"(db), "n"(HB), "n"(1));
  }
  template <uint32_t HB>
  static __device__ __forceinline__ void set(float* d, const uint32_t* a, uint32_t db) {
    asm volatile("{\n.reg .pred p;\n.reg .b64 db;\nsetp.ne.b32 p, %38, 0;\n"
      "mov.b64 db, {%36, %37};\n"
      "wgmma.mma_async.sync.aligned.m64n64k16.f32.bf16.bf16 {"
      "%0, %1, %2, %3, %4, %5, %6, %7, %8, %9, %10, %11, %12, %13, %14, %15, "
      "%16, %17, %18, %19, %20, %21, %22, %23, %24, %25, %26, %27, %28, %29, %30, %31"
      "}, {%32, %33, %34, %35}, db, p, 1, 1, 1;\n}\n"
      : "=f"(d[0]), "=f"(d[1]), "=f"(d[2]), "=f"(d[3]), "=f"(d[4]), "=f"(d[5]), "=f"(d[6]), "=f"(d[7]),
        "=f"(d[8]), "=f"(d[9]), "=f"(d[10]), "=f"(d[11]), "=f"(d[12]), "=f"(d[13]), "=f"(d[14]), "=f"(d[15]),
        "=f"(d[16]), "=f"(d[17]), "=f"(d[18]), "=f"(d[19]), "=f"(d[20]), "=f"(d[21]), "=f"(d[22]), "=f"(d[23]),
        "=f"(d[24]), "=f"(d[25]), "=f"(d[26]), "=f"(d[27]), "=f"(d[28]), "=f"(d[29]), "=f"(d[30]), "=f"(d[31])
      : "r"(a[0]), "r"(a[1]), "r"(a[2]), "r"(a[3]), "r"(db), "n"(HB), "n"(0));
  }
};
template <> struct WgSST<48> {
  template <uint32_t HA, uint32_t HB>
  static __device__ __forceinline__ void mma(float* d, uint32_t da, uint32_t db, int sc) {
    asm volatile("{\n.reg .pred p;\n.reg .b64 da, db;\nsetp.ne.b32 p, %28, 0;\n"
      "mov.b64 da, {%24, %25};\nmov.b64 db, {%26, %27};\n"
      "wgmma.mma_async.sync.aligned.m64n48k16.f32.bf16.bf16 {"
      "%0, %1, %2, %3, %4, %5, %6, %7, %8, %9, %10, %11, %12, %13, %14, %15, "
      "%16, %17, %18, %19, %20, %21, %22, %23"
      "}, da, db, p, 1, 1, 0, 1;\n}\n"
      : "+f"(d[0]), "+f"(d[1]), "+f"(d[2]), "+f"(d[3]), "+f"(d[4]), "+f"(d[5]), "+f"(d[6]), "+f"(d[7]),
        "+f"(d[8]), "+f"(d[9]), "+f"(d[10]), "+f"(d[11]), "+f"(d[12]), "+f"(d[13]), "+f"(d[14]), "+f"(d[15]),
        "+f"(d[16]), "+f"(d[17]), "+f"(d[18]), "+f"(d[19]), "+f"(d[20]), "+f"(d[21]), "+f"(d[22]), "+f"(d[23])
      : "r"(da), "n"(HA), "r"(db), "n"(HB), "r"(sc));
  }
};
template <> struct WgSST<80> {
  template <uint32_t HA, uint32_t HB>
  static __device__ __forceinline__ void mma(float* d, uint32_t da, uint32_t db, int sc) {
    asm volatile("{\n.reg .pred p;\n.reg .b64 da, db;\nsetp.ne.b32 p, %44, 0;\n"
      "mov.b64 da, {%40, %41};\nmov.b64 db, {%42, %43};\n"
      "wgmma.mma_async.sync.aligned.m64n80k16.f32.bf16.bf16 {"
      "%0, %1, %2, %3, %4, %5, %6, %7, %8, %9, %10, %11, %12, %13, %14, %15, "
      "%16, %17, %18, %19, %20, %21, %22, %23, %24, %25, %26, %27, %28, %29, %30, %31, "
      "%32, %33, %34, %35, %36, %37, %38, %39"
      "}, da, db, p, 1, 1, 0, 1;\n}\n"
      : "+f"(d[0]), "+f"(d[1]), "+f"(d[2]), "+f"(d[3]), "+f"(d[4]), "+f"(d[5]), "+f"(d[6]), "+f"(d[7]),
        "+f"(d[8]), "+f"(d[9]), "+f"(d[10]), "+f"(d[11]), "+f"(d[12]), "+f"(d[13]), "+f"(d[14]), "+f"(d[15]),
        "+f"(d[16]), "+f"(d[17]), "+f"(d[18]), "+f"(d[19]), "+f"(d[20]), "+f"(d[21]), "+f"(d[22]), "+f"(d[23]),
        "+f"(d[24]), "+f"(d[25]), "+f"(d[26]), "+f"(d[27]), "+f"(d[28]), "+f"(d[29]), "+f"(d[30]), "+f"(d[31]),
        "+f"(d[32]), "+f"(d[33]), "+f"(d[34]), "+f"(d[35]), "+f"(d[36]), "+f"(d[37]), "+f"(d[38]), "+f"(d[39])
      : "r"(da), "n"(HA), "r"(db), "n"(HB), "r"(sc));
  }
};
template <> struct WgSST<192> {
  template <uint32_t HA, uint32_t HB>
  static __device__ __forceinline__ void mma(float* d, uint32_t da, uint32_t db, int sc) {
    asm volatile("{\n.reg .pred p;\n.reg .b64 da, db;\nsetp.ne.b32 p, %100, 0;\n"
      "mov.b64 da, {%96, %97};\nmov.b64 db, {%98, %99};\n"
      "wgmma.mma_async.sync.aligned.m64n192k16.f32.bf16.bf16 {"
      "%0, %1, %2, %3, %4, %5, %6, %7, %8, %9, %10, %11, %12, %13, %14, %15, "
      "%16, %17, %18, %19, %20, %21, %22, %23, %24, %25, %26, %27, %28, %29, %30, %31, "
      "%32, %33, %34, %35, %36, %37, %38, %39, %40, %41, %42, %43, %44, %45, %46, %47, "
      "%48, %49, %50, %51, %52, %53, %54, %55, %56, %57, %58, %59, %60, %61, %62, %63, "
      "%64, %65, %66, %67, %68, %69, %70, %71, %72, %73, %74, %75, %76, %77, %78, %79, "
      "%80, %81, %82, %83, %84, %85, %86, %87, %88, %89, %90, %91, %92, %93, %94, %95"
      "}, da, db, p, 1, 1, 0, 1;\n}\n"
      : "+f"(d[0]), "+f"(d[1]), "+f"(d[2]), "+f"(d[3]), "+f"(d[4]), "+f"(d[5]), "+f"(d[6]), "+f"(d[7]),
        "+f"(d[8]), "+f"(d[9]), "+f"(d[10]), "+f"(d[11]), "+f"(d[12]), "+f"(d[13]), "+f"(d[14]), "+f"(d[15]),
        "+f"(d[16]), "+f"(d[17]), "+f"(d[18]), "+f"(d[19]), "+f"(d[20]), "+f"(d[21]), "+f"(d[22]), "+f"(d[23]),
        "+f"(d[24]), "+f"(d[25]), "+f"(d[26]), "+f"(d[27]), "+f"(d[28]), "+f"(d[29]), "+f"(d[30]), "+f"(d[31]),
        "+f"(d[32]), "+f"(d[33]), "+f"(d[34]), "+f"(d[35]), "+f"(d[36]), "+f"(d[37]), "+f"(d[38]), "+f"(d[39]),
        "+f"(d[40]), "+f"(d[41]), "+f"(d[42]), "+f"(d[43]), "+f"(d[44]), "+f"(d[45]), "+f"(d[46]), "+f"(d[47]),
        "+f"(d[48]), "+f"(d[49]), "+f"(d[50]), "+f"(d[51]), "+f"(d[52]), "+f"(d[53]), "+f"(d[54]), "+f"(d[55]),
        "+f"(d[56]), "+f"(d[57]), "+f"(d[58]), "+f"(d[59]), "+f"(d[60]), "+f"(d[61]), "+f"(d[62]), "+f"(d[63]),
        "+f"(d[64]), "+f"(d[65]), "+f"(d[66]), "+f"(d[67]), "+f"(d[68]), "+f"(d[69]), "+f"(d[70]), "+f"(d[71]),
        "+f"(d[72]), "+f"(d[73]), "+f"(d[74]), "+f"(d[75]), "+f"(d[76]), "+f"(d[77]), "+f"(d[78]), "+f"(d[79]),
        "+f"(d[80]), "+f"(d[81]), "+f"(d[82]), "+f"(d[83]), "+f"(d[84]), "+f"(d[85]), "+f"(d[86]), "+f"(d[87]),
        "+f"(d[88]), "+f"(d[89]), "+f"(d[90]), "+f"(d[91]), "+f"(d[92]), "+f"(d[93]), "+f"(d[94]), "+f"(d[95])
      : "r"(da), "n"(HA), "r"(db), "n"(HB), "r"(sc));
  }
};

struct FftConst {
  uint32_t f[2][4], fi[4][4];
  uint32_t ta[2][2], tb[2][2];
};
__device__ __forceinline__ void cis(int m, float scale, float& c, float& s) {
  const float a = (float)m * (-6.283185307179586f * scale);
  c = __cosf(a);
  s = __sinf(a);
}
__device__ __forceinline__ void fft_tables(uint32_t (&v)[12], int tw) {
  const int row = tw >> 2, ch = tw & 3;
#pragma unroll
  for (int i = 0; i < 4; i++) {
    float c[2], s[2], x[2];
#pragma unroll
    for (int e = 0; e < 2; e++) {
      cis((((32 * (8 * ch + 2 * i + e) + 15) * (4 * row - 63) + 2048) & 4095) - 2048, 1.f / 4096, c[e], s[e]);
      float gc, gs;
      cis((((row & 15) * (8 * (ch & 1) + 2 * i + e) + 8) & 15) - 8, 1.f / 16, gc, gs);
      x[e] = (row >> 4) == (ch >> 1) ? gc : (ch >> 1) ? gs : -gs;
    }
    v[i] = pack2(c[0] * 0.125f, c[1] * 0.125f);
    v[4 + i] = pack2(s[0] * 0.125f, s[1] * 0.125f);
    v[8 + i] = pack2(x[0], x[1]);
  }
#pragma unroll
  for (int i = 0; i < 12; i++) asm volatile("" : "+r"(v[i]));
}
__device__ __forceinline__ void fft_tables_store(const uint32_t (&v)[12], uint32_t sb, int tw) {
  const int row = tw >> 2;
  const uint32_t x = ((tw ^ (row >> 1)) & 3) << 4, a = sb + OFF_FT + (16 * (row >> 3) + (row & 7)) * 64 + x;
  sts128(a, v[0], v[1], v[2], v[3]);
  sts128(a + 512, v[4], v[5], v[6], v[7]);
  sts128(sb + OFF_GT + row * 64 + x, v[8], v[9], v[10], v[11]);
}
__device__ __forceinline__ void fft_twiddles(uint32_t (&v)[2], int tw) {
  float a[2], s[2];
#pragma unroll
  for (int i = 0; i < 2; i++) {
    float c;
    cis((2 * (2 * (tw & 3) + i) - 15) * (4 * (tw >> 2) - 63), 1.f / 4096, c, s[i]);
    a[i] = __fdividef(-s[i], 1.f + c);
  }
  v[0] = pack2(a[0], a[1]);
  v[1] = pack2(s[0], s[1]);
  asm volatile("" : "+r"(v[0]), "+r"(v[1]));
}
__device__ __forceinline__ void fft_matrices(FftConst& k, uint32_t sb, int w, int lane) {
  const uint32_t x = (lane >> 1) & 3;
  const uint2 t0 = lds64(sb + OFF_TT + 256 * w + 8 * lane), t1 = lds64(sb + OFF_TT + 256 * w + 8 * (lane ^ 3));
  k.ta[0][0] = t0.x;
  k.tb[0][0] = t0.y;
  k.ta[1][1] = __byte_perm(t1.x, 0, 0x1032);
  k.tb[1][1] = __byte_perm(t1.y, 0, 0x1032);
#pragma unroll
  for (int j = 0; j < 2; j++) {
    k.ta[1 - j][j] = k.ta[j][j] ^ 0x80008000u;
    k.tb[1 - j][j] = k.tb[j][j] ^ 0x80008000u;
    asm volatile("" : "+r"(k.ta[0][j]), "+r"(k.tb[0][j]), "+r"(k.ta[1][j]), "+r"(k.tb[1][j]));
  }
#pragma unroll
  for (int i = 0; i < 2; i++) {
    ldsm4(k.f[i], sb + OFF_FT + (16 * w + (lane & 15)) * 64 + (((2 * i + (lane >> 4)) ^ x) << 4));
    ldsm4t(k.fi[i], sb + OFF_FT + (32 * i + lane) * 64 + ((w ^ x) << 4));
#pragma unroll
    for (int j = 0; j < 4; j++) {
      k.fi[2 + i][j] = (j & 1) ? k.fi[i][j - 1] ^ 0x80008000u : k.fi[i][j + 1];
      asm volatile("" : "+r"(k.fi[2 + i][j]));
    }
  }
}
__device__ __forceinline__ void rot(uint32_t& x, uint32_t& y, uint32_t a, uint32_t b) {
  x = bfma(a, y, x);
  y = bfma(b, x, y);
  x = bfma(a, y, x);
}
__device__ __forceinline__ void twiddle_fwd(uint32_t (&a)[4][4], float* d, const FftConst& k) {
#pragma unroll
  for (int q = 0; q < 4; q++)
#pragma unroll
    for (int j = 0; j < 2; j++) {
      const float* x = d + 8 * q + 4 * j;
      uint32_t re = pack2(x[0], x[1]), im = pack2(x[2], x[3]);
      rot(re, im, k.ta[0][j], k.tb[0][j]);
      a[q & 2][2 * j + (q & 1)] = re;
      a[(q & 2) + 1][2 * j + (q & 1)] = im;
    }
}
__device__ __forceinline__ void g_step(float* d, const uint32_t (&a)[4][4], uint32_t dre, uint32_t dim) {
  WgRS<32>::set<HI_SW64>(d, a[0], dre);
  WgRS<32>::set<HI_SW64>(d + 16, a[2], dre);
  WgRS<32>::mma<HI_SW64>(d, a[1], dim);
  WgRS<32>::mma<HI_SW64>(d + 16, a[3], dim);
  wg_commit();
}

__device__ __forceinline__ void products(uint32_t (&a)[4][4], const float* H, const float* U, int p) {
#pragma unroll
  for (int j = 0; j < 2; j++)
#pragma unroll
    for (int m = 2 * p; m < 2 * p + 2; m++) {
      float pr[2], pi[2];
#pragma unroll
      for (int x = 0; x < 2; x++)
#pragma unroll
        for (int q = 0; q <= m; q++) {
          const int ih = 16 * (q >> 1) + 2 * (q & 1) + 4 * j + x, iu = 16 * ((m - q) >> 1) + 2 * ((m - q) & 1) + 4 * j + x;
          pr[x] = q ? fmaf(H[ih], U[iu], pr[x]) : H[ih] * U[iu];
          pi[x] = q ? fmaf(H[ih], U[iu + 8], pi[x]) : H[ih] * U[iu + 8];
          pr[x] = fmaf(-H[ih + 8], U[iu + 8], pr[x]);
          pi[x] = fmaf(H[ih + 8], U[iu], pi[x]);
        }
      a[m & 2][2 * j + (m & 1)] = pack2(pr[0], pr[1]);
      a[(m & 2) + 1][2 * j + (m & 1)] = pack2(pi[0], pi[1]);
    }
}

__device__ __forceinline__ void f_step(float* d, const FftConst& k, uint32_t db) {
  WgRS<64>::set<HI_SW32>(d, k.f[0], db);
  WgRS<64>::mma<HI_SW32>(d, k.f[1], db + 32);
  wg_commit();
}
__device__ __forceinline__ void last_step(float* d, const FftConst& k, uint32_t dz) {
  wg_fence();
  WgRS<64>::set<HI_SW128>(d, k.fi[0], dz);
#pragma unroll
  for (int ks = 1; ks < 4; ks++) WgRS<64>::mma<HI_SW128>(d, k.fi[ks], dz + 128 * ks);
  wg_commit();
}
__device__ __forceinline__ void conv_channel(const FftConst& k, uint32_t (&a)[4][4], uint32_t sb, int c, int cn, int wg, int w, int lane) {
  const uint32_t cb = sb + off_ch(c), bars = sb + OFF_BAR;
  const uint32_t du = desc_lo(cb, 1024), dg = desc_lo(sb + OFF_GT, 16), dz = desc_lo(cb + U_BYTES, 16);
  float U[32], H[32];
  uint32_t e[4][4];
  const float dv = __uint_as_float(lds32(sb + OFF_D + 4 * c));
  mbar_wait(bars + 8 * (B_U + (c < 3 ? c : 3)), 0);
  TSM(w == 0 && c < 3, 7 + wg);
  wg_fence();
  f_step(U, k, du);
  g_step(H, a, dg, dg + 64);
  wg_wait<1>();
  pin<32>(U);
  twiddle_fwd(e, U, k);
  wg_fence();
  g_step(U, e, dg, dg + 64);
  wg_wait<0>();
  pin<32>(U);
  pin<32>(H);
#pragma unroll
  for (int j = 0; j < 4; j++) H[4 * (j >> 1) + (j & 1)] += dv;
  float V[32];
#pragma unroll
  for (int p = 0; p < 2; p++) {
    products(a, H, U, p);
    wg_fence();
    WgRS<32>::set<HI_SW64>(V + 16 * p, a[2 * p], dg + 64);
    WgRS<32>::mma<HI_SW64>(V + 16 * p, a[2 * p + 1], dg);
    wg_commit();
  }
  const uint32_t za = cb + U_BYTES + (8 * w + (lane & 7)) * 128 + (((lane >> 3) ^ (lane & 7)) << 4);
  const uint32_t ya = cb + (lane >> 4) * 1024 + (8 * w + (lane & 7)) * 32 + ((((lane >> 3) ^ (lane >> 2)) & 1) << 4);
  wg_sync(1 + wg);
#pragma unroll
  for (int p = 0; p < 2; p++) {
    if (p == 0) wg_wait<1>();
    else wg_wait<0>();
    pin<16>(V + 16 * p);
#pragma unroll
    for (int i = 0; i < 4; i++) {
      const int j = i & 1;
      const float* x = V + 16 * p + 4 * j + (i & 2);
      e[p][i] = pack2(x[8], x[9]);
      e[2 + p][i] = pack2(x[0], x[1]);
      rot(e[p][i], e[2 + p][i], k.ta[1][j], k.tb[1][j]);
    }
    stsm4(za ^ (64 * p), e[p]);
    stsm4((za ^ (64 * p)) + 4096, e[2 + p]);
  }
  if (cn >= 0) {
    wg_fence();
    f_step(U, k, desc_lo(sb + off_ch(cn) + U_BYTES, 1024));
    fence_async_smem();
    wg_sync(1 + wg);
    last_step(H, k, dz);
    wg_wait<1>();
    pin<32>(U);
    twiddle_fwd(a, U, k);
    wg_wait<0>();
  } else {
    fence_async_smem();
    wg_sync(1 + wg);
    last_step(H, k, dz);
    wg_wait<0>();
  }
  pin<32>(H);
  if (lane == 0) mbar_arrive(bars + 8 * B_CVD);
  TSIF(w == 0, 88 + c);
#pragma unroll
  for (int j = 0; j < 8; j++)
    e[j >> 2][j & 3] = j < 2 ? pack2(H[4 * j], H[4 * j + 1]) : pack2(H[4 * j] + H[4 * j - 6], H[4 * j + 1] + H[4 * j - 5]);
  stsm4(ya, e[0]);
  stsm4(ya + 2048, e[1]);
  fence_async_smem();
  __syncwarp();
}

__device__ __forceinline__ void prep_slab(uint4* res, const uint2* sw, uint32_t sb, int slab, int w, int lane) {
  const int t = lane & 3, tp = (lane & 7) >> 1, pos = 8 * tp + 2 * (((lane >> 3) + tp) & 3) + (lane & 1);
  const uint32_t base = sb + OFF_KVS + slab * KVS_BYTES + pos * 128;
  uint32_t kk[2][4][4], vv[2][4];
  mbar_wait(sb + OFF_BAR + 8 * (B_KV + slab), 0);
#pragma unroll
  for (int h = 0; h < 2; h++) {
#pragma unroll
    for (int j = 0; j < 4; j++) {
      const uint32_t a = base + 128 * j;
      ldsm4t(kk[h][j], a + (((w + 4 * h) ^ ((a >> 7) & 7)) << 4));
    }
    const uint32_t a = base + KVS_V;
    ldsm4t(vv[h], a + (((w + 4 * h) ^ ((a >> 7) & 7)) << 4));
  }
#pragma unroll
  for (int h = 0; h < 2; h++) {
    uint32_t (&k)[4][4] = kk[h];
    uint32_t (&v)[4] = vv[h];
    const uint32_t w0 = __byte_perm(sw[h].x, 0, 0x1010), w1 = __byte_perm(sw[h].x, 0, 0x3232);
    const uint32_t w2 = __byte_perm(sw[h].y, 0, 0x1010), w3 = __byte_perm(sw[h].y, 0, 0x3232);
#pragma unroll
    for (int m = 0; m < 4; m++)
      v[m] = bmul(badd(badd(badd(bmul(k[0][m], w3), bmul(k[1][m], w2)), bmul(k[2][m], w1)), bmul(k[3][m], w0)), v[m]);
    uint32_t a[4];
#pragma unroll
    for (int m = 0; m < 4; m++) a[m] = (t & 1) ? v[(m + 3) & 3] : v[m];
    res[h] = (t & 2) ? make_uint4(a[2], a[3], a[0], a[1]) : make_uint4(a[0], a[1], a[2], a[3]);
  }
}

__device__ __forceinline__ void prep_gate(const Params& p, uint32_t sb, int b, int w, int lane) {
  uint2 gw[5], x[4][5];
#pragma unroll
  for (int j = 0; j < 5; j++) gw[j] = ldg64(reinterpret_cast<const uint2*>(p.gate_w) + lane + 32 * j);
#pragma unroll
  for (int i = 0; i < 4; i++)
#pragma unroll
    for (int j = 0; j < 5; j++)
      x[i][j] = ldg64(reinterpret_cast<const uint2*>(p.q) + (16 * b + 4 * w + i) * (DIM / 4) + lane + 32 * j);
  float s[4];
#pragma unroll
  for (int i = 0; i < 4; i++) {
    s[i] = 0.f;
#pragma unroll
    for (int j = 0; j < 5; j++) {
      const uint32_t m0 = bmul(x[i][j].x, gw[j].x), m1 = bmul(x[i][j].y, gw[j].y);
      s[i] += (bf_lo(m0) + bf_hi(m0)) + (bf_lo(m1) + bf_hi(m1));
    }
  }
  const bool h = lane & 16, q = lane & 8;
  const float a = (h ? s[2] : s[0]) + __shfl_xor_sync(0xffffffffu, h ? s[0] : s[2], 16);
  const float c = (h ? s[3] : s[1]) + __shfl_xor_sync(0xffffffffu, h ? s[1] : s[3], 16);
  float z = (q ? c : a) + __shfl_xor_sync(0xffffffffu, q ? a : c, 8);
#pragma unroll
  for (int o = 4; o > 0; o >>= 1) z += __shfl_xor_sync(0xffffffffu, z, o);
  z = bf_lo(pack2(z, 0.f));
  z = bf_lo(pack2(__fdividef(1.f, 1.f + __expf(-z)), 0.f));
  mbar_wait(sb + OFF_BAR + 8 * B_S3, 0);
  if ((lane & 7) == 0) asm volatile("st.shared.f32 [%0], %1;" ::"r"(sb + OFF_GATE + 64 * (b & 7) + 16 * w + (lane >> 1)), "f"(z) : "memory");
  fence_async_smem();
}

__device__ __forceinline__ uint32_t bmax(uint32_t a, uint32_t b) {
  uint32_t d;
  asm("max.bf16x2 %0, %1, %2;" : "=r"(d) : "r"(a), "r"(b));
  return d;
}
__device__ __forceinline__ void softmax_two(const float (&l)[2][2], uint32_t& p0, uint32_t& p1) {
  constexpr float kScale = 0.22360679774997896f, kLog2e = 1.4426950408889634f;
  const uint32_t r0 = pack2(l[0][0], l[1][0]), r1 = pack2(l[0][1], l[1][1]);
  const uint32_t x0 = pack2(bf_lo(r0) * kScale, bf_hi(r0) * kScale), x1 = pack2(bf_lo(r1) * kScale, bf_hi(r1) * kScale);
  uint32_t m = bmax(x0, x1);
  m = bmax(m, __shfl_xor_sync(0xffffffffu, m, 1));
  m = bmax(m, __shfl_xor_sync(0xffffffffu, m, 2));
  const float m0 = bf_lo(m) * kLog2e, m1 = bf_hi(m) * kLog2e;
  p0 = pack2(ex2(bf_lo(x0) * kLog2e - m0), ex2(bf_lo(x1) * kLog2e - m0));
  p1 = pack2(ex2(bf_hi(x0) * kLog2e - m1), ex2(bf_hi(x1) * kLog2e - m1));
}

__device__ __forceinline__ void halo_read(uint32_t (&kpv)[10], uint32_t (&vpv)[10], uint32_t (&tg)[7], const uint4* hp) {
#pragma unroll
  for (int j = 0; j < 7; j++) {
    uint32_t x0, x1, x2;
    asm volatile("ld.relaxed.gpu.global.v4.u32 {%0, %1, %2, %3}, [%4];"
                 : "=r"(x0), "=r"(x1), "=r"(x2), "=r"(tg[j]) : "l"(hp + 32 * j) : "memory");
    if (j < 4) kpv[3 * j] = x0; else vpv[3 * j - 10] = x0;
    if (j < 3) kpv[3 * j + 1] = x1; else vpv[3 * j - 9] = x1;
    if (j < 3) kpv[3 * j + 2] = x2; else if (j < 6) vpv[3 * j - 8] = x2;
  }
}

template <int ROT>
__device__ __forceinline__ void pack_qkv(const float* acc, uint32_t (&qlo)[10], uint32_t (&qhi)[10], uint32_t (&klo)[10],
                                         uint32_t (&khi)[10], uint32_t (&vlo)[10], uint32_t (&vhi)[10]) {
#pragma unroll
  for (int j = 0; j < 10; j++) {
    const int x = (j + ROT) % 10, tq = x < 8 ? x : 16 + x, tk = x < 8 ? 8 + x : 18 + x, tv = x < 8 ? 16 + x : 20 + x;
    khi[j] = pack2(acc[4 * tk + 2], acc[4 * tk + 3]);
    vhi[j] = movm(pack2(acc[4 * tv + 2], acc[4 * tv + 3]));
    qlo[j] = pack2(acc[4 * tq], acc[4 * tq + 1]);
    qhi[j] = pack2(acc[4 * tq + 2], acc[4 * tq + 3]);
    klo[j] = pack2(acc[4 * tk], acc[4 * tk + 1]);
    vlo[j] = pack2(acc[4 * tv], acc[4 * tv + 1]);
    asm volatile("" : "+r"(khi[j]), "+r"(qlo[j]), "+r"(qhi[j]), "+r"(klo[j]), "+r"(vlo[j]));
  }
}

template <int ROT> __device__ __forceinline__ void halo_send(const float* acc, uint4* ho, uint32_t tag) {
#pragma unroll
  for (int j = 0; j < 7; j++) {
    uint32_t x[3];
#pragma unroll
    for (int e = 0; e < 3; e++) {
      const int i = 3 * j + e, y = (i % 10 + ROT) % 10, tk = y < 8 ? 8 + y : 18 + y, tv = y < 8 ? 16 + y : 20 + y;
      x[e] = i < 10 ? pack2(acc[4 * tk + 2], acc[4 * tk + 3]) : i < 20 ? movm(pack2(acc[4 * tv + 2], acc[4 * tv + 3])) : 0u;
    }
    asm volatile("st.relaxed.gpu.global.v4.u32 [%0], {%1, %2, %3, %4};" ::"l"(ho + 32 * j), "r"(x[0]), "r"(x[1]), "r"(x[2]), "r"(tag) : "memory");
  }
}

__device__ __forceinline__ void attention(float* acc, uint32_t sb, int b, int par, int w, int lane, uint32_t tag) {
  const int g = lane >> 2, t = lane & 3;
  uint32_t klo[10], khi[10], vlo[10], vhi[10], qlo[10], qhi[10], kpv[10], vpv[10];
  if (w == 3 && b < NCTA - 8) {
    uint4* ho = g_halo + (b * 2 + par) * 224 + lane;
    if (tail_first(b & 7)) halo_send<8>(acc, ho, tag);
    else halo_send<0>(acc, ho, tag);
    TSIF(par == 0, 76);
    pin<120>(acc);
  }
  if (tail_first(b & 7)) pack_qkv<8>(acc, qlo, qhi, klo, khi, vlo, vhi);
  else pack_qkv<0>(acc, qlo, qhi, klo, khi, vlo, vhi);
  const uint32_t xa = sb + OFF_KVX + (par * 3) * 2560 + lane * 16;
  if (w < 3) {
    sts128(xa + w * 2560, khi[0], khi[1], khi[2], khi[3]);
    sts128(xa + w * 2560 + 512, khi[4], khi[5], khi[6], khi[7]);
    sts128(xa + w * 2560 + 1024, khi[8], khi[9], vhi[0], vhi[1]);
    sts128(xa + w * 2560 + 1536, vhi[2], vhi[3], vhi[4], vhi[5]);
    sts128(xa + w * 2560 + 2048, vhi[6], vhi[7], vhi[8], vhi[9]);
  }
  TSIF(par == 0 && w == 1, 64);
#pragma unroll
  for (int j = 0; j < 10; j++) vlo[j] = movm(vlo[j]);
  const bool far0 = 2 * t > g, far1 = 2 * t + 1 > g;
  const uint32_t mfar = (far0 ? 0x0000FFFFu : 0u) | (far1 ? 0xFFFF0000u : 0u);
  float slo[4][2], lg[2][2];
  uint32_t phi[4], plo[4], qml[4], qmh[4];
#pragma unroll
  for (int h = 0; h < 4; h++) {
    const int f = h == 0 ? 0 : h == 1 ? 3 : h == 2 ? 5 : 8, hf = h < 2 ? 2 : 7;
    const bool mine = (h & 1) ? t >= 2 : t < 2;
    qml[h] = mine ? qlo[hf] : 0u;
    qmh[h] = mine ? qhi[hf] : 0u;
    float a[4] = {0.f, 0.f, 0.f, 0.f}, c[4] = {0.f, 0.f, 0.f, 0.f};
    mma16816(a, qlo[f], qhi[f], qlo[f + 1], qhi[f + 1], klo[f], klo[f + 1]);
    mma16816(c, qlo[f], qhi[f], qlo[f + 1], qhi[f + 1], khi[f], khi[f + 1]);
    mma1688(a, qml[h], qmh[h], klo[hf]);
    mma1688(c, qml[h], qmh[h], khi[hf]);
    slo[h][0] = a[0];
    slo[h][1] = a[1];
    lg[h & 1][0] = far0 ? a[2] : c[2];
    lg[h & 1][1] = far1 ? a[3] : c[3];
    if (h & 1) softmax_two(lg, phi[h - 1], phi[h]);
  }
  TSIF(par == 0 && w == 1, 65);
  wg_sync(1 + par);
  TSIF(par == 0 && w == 1, 66);
  const bool nohist = (w == 0) && (b < 8);
  const uint4* hp = g_halo + ((b - 8) * 2 + par) * 224 + lane;
  uint32_t tg[7];
  if (w > 0) {
    const uint4 v0 = lds128(xa + (w - 1) * 2560), v1 = lds128(xa + (w - 1) * 2560 + 512), v2 = lds128(xa + (w - 1) * 2560 + 1024);
    const uint4 v3 = lds128(xa + (w - 1) * 2560 + 1536), v4 = lds128(xa + (w - 1) * 2560 + 2048);
    kpv[0] = v0.x; kpv[1] = v0.y; kpv[2] = v0.z; kpv[3] = v0.w; kpv[4] = v1.x; kpv[5] = v1.y; kpv[6] = v1.z; kpv[7] = v1.w;
    kpv[8] = v2.x; kpv[9] = v2.y; vpv[0] = v2.z; vpv[1] = v2.w; vpv[2] = v3.x; vpv[3] = v3.y; vpv[4] = v3.z; vpv[5] = v3.w;
    vpv[6] = v4.x; vpv[7] = v4.y; vpv[8] = v4.z; vpv[9] = v4.w;
  } else if (nohist) {
#pragma unroll
    for (int j = 0; j < 10; j++) kpv[j] = vpv[j] = 0u;
  } else {
    TSIF(par == 0, 77);
    halo_read(kpv, vpv, tg, hp);
  }
  if (w == 0 && !nohist) {
    int spins = 0;
    while (true) {
      bool ok = true;
#pragma unroll
      for (int j = 0; j < 7; j++) ok = ok && tg[j] == tag;
      if (__all_sync(0xffffffffu, ok) || ++spins > SPIN_LIMIT) break;
      halo_read(kpv, vpv, tg, hp);
    }
    TSIF(par == 0, 79);
  }
#pragma unroll
  for (int h = 0; h < 4; h++) {
    const int f = h == 0 ? 0 : h == 1 ? 3 : h == 2 ? 5 : 8, hf = h < 2 ? 2 : 7;
    float a[4] = {0.f, 0.f, 0.f, 0.f};
    mma16816(a, qlo[f], qhi[f], qlo[f + 1], qhi[f + 1], kpv[f], kpv[f + 1]);
    mma1688(a, qml[h], qmh[h], kpv[hf]);
    const float ninf = __int_as_float(0xff800000);
    lg[h & 1][0] = far0 ? (nohist ? ninf : a[0]) : slo[h][0];
    lg[h & 1][1] = far1 ? (nohist ? ninf : a[1]) : slo[h][1];
    if (h & 1) softmax_two(lg, plo[h - 1], plo[h]);
  }
  TSIF(par == 0 && w <= 1, 67 + w);
  uint32_t ov[20];
#pragma unroll
  for (int hp = 0; hp < 2; hp++) {
    const int hf = hp ? 7 : 2;
    float sh[4] = {0.f, 0.f, 0.f, 0.f}, i0 = 0.f, i1 = 0.f;
#pragma unroll
    for (int e = 0; e < 2; e++) {
      const int h = 2 * hp + e, f = h == 0 ? 0 : h == 1 ? 3 : h == 2 ? 5 : 8;
      const uint32_t a0 = plo[h] & mfar, a2 = plo[h] & ~mfar, a3 = phi[h] & mfar, c1 = phi[h] & ~mfar;
      float sum[4] = {0.f, 0.f, 0.f, 0.f};
      mma1688(sum, plo[h], phi[h], 0x3F803F80u);
      const float r0 = rcp(sum[0]), r1 = rcp(sum[2]);
#pragma unroll
      for (int j = f; j < f + 2; j++) {
        float o[4] = {0.f, 0.f, 0.f, 0.f};
        mma16816(o, a0, 0u, a2, a3, vpv[j], vlo[j]);
        mma1688(o, 0u, c1, vhi[j]);
        ov[2 * j] = pack2(o[0] * r0, o[1] * r0);
        ov[2 * j + 1] = pack2(o[2] * r1, o[3] * r1);
      }
      const bool mine = e ? g >= 4 : g < 4;
      mma16816(sh, a0, 0u, a2, a3, mine ? vpv[hf] : 0u, mine ? vlo[hf] : 0u);
      mma1688(sh, 0u, c1, mine ? vhi[hf] : 0u);
      if (e == 0 || t >= 2) {
        i0 = r0;
        i1 = r1;
      }
    }
    ov[2 * hf] = pack2(sh[0] * i0, sh[1] * i0);
    ov[2 * hf + 1] = pack2(sh[2] * i1, sh[3] * i1);
  }
  TS(32 + 4 * par + w);
  mbar_wait(sb + OFF_BAR + 8 * B_P1, 0);
  const uint32_t oa = sb + OFF_OA + (lane >> 4) * 2048 + (32 * w + 2 * (lane & 15) + par) * 16;
#pragma unroll
  for (int j = 0; j < 5; j++) stsm4(oa + 4096 * j, ov + 4 * j);
  TSIF(par == 0 && w == 0, 120);
  fence_async_smem();
  TSIF(par == 0 && w == 0, 121);
  __syncwarp();
  if (lane == 0) mbar_arrive(sb + OFF_BAR + 8 * B_ATTN);
  TSM(w == 0 || w == 2, 122 + par + (w == 2 ? 3 : 0));
}

struct Maps {
  CUtensorMap x, wm, wt, k, v, y, wo, qm, qt, om, ot, yl, ol;
};

__device__ __forceinline__ void load_stage(uint32_t sb, int kb, int b, const Maps& m) {
  const uint32_t st = sb + (kb & 3) * STAGE_BYTES, bar = sb + OFF_BAR + 8 * (B_FULL1 + (kb & 3));
  const int r = b >> 3, hg = b & 7, slab = kb - KV_KB;
  const bool kv = slab >= 0 && slab < 5;
  const uint32_t kbar = sb + OFF_BAR + 8 * (B_KV + slab), dst = sb + OFF_KVS + slab * KVS_BYTES;
  mbar_expect_tx(bar, STAGE_BYTES);
  if (kv) mbar_expect_tx(kbar, KVS_BYTES);
  tma_3d(st, &m.x, 64 * kb, 64 * r, 0, bar);
  tma_3d(st + ST_W, &m.wm, 80 * hg + (tail_first(hg) ? 16 : 0), 64 * kb, 0, bar);
  tma_3d(st + ST_WT, &m.wt, 80 * hg + (tail_first(hg) ? 0 : 64), 64 * kb, 0, bar);
  if (kv) tma_3d(dst, &m.k, 0, 32 * (b >> 1) - 3, 2 * slab + (b & 1), kbar);
  if (kv) tma_3d(dst + KVS_V, &m.v, 0, 32 * (b >> 1), 2 * slab + (b & 1), kbar);
}

__global__ void __launch_bounds__(NTHR, 1) fused_kernel(const __grid_constant__ Maps m, const Params p) {
  extern __shared__ __align__(1024) uint8_t smem[];
  const uint32_t sb = (uint32_t)__cvta_generic_to_shared(smem);
  const uint32_t bars = sb + OFF_BAR;
  const int tid = threadIdx.x, lane = tid & 31;
  int b = blockIdx.x;
  b = (((b & 63) >> 3) * 2 + (b & 1)) * 8 + (((b < 64 ? 0x6521 : 0x7430) >> (4 * ((b >> 1) & 3))) & 7);
  const int r = b >> 3, hg = b & 7;

  if (tid == T_ISSUE) {
    TSM(true, 0);
    mbar_init(bars + 8 * B_F0, 1);
    fence_async_smem();
    mbar_expect_tx(bars + 8 * B_F0, ST_WT);
    tma_3d(sb, &m.x, 0, 64 * r, 0, bars + 8 * B_F0);
    tma_3d(sb + ST_W, &m.wm, 80 * hg + (tail_first(hg) ? 16 : 0), 0, 0, bars + 8 * B_F0);
#pragma unroll
    for (int i = 0; i < 4; i++) mbar_init(bars + 8 * (B_FULL1 + i), 1);
    fence_async_smem();
    mbar_expect_tx(bars + 8 * B_FULL1, STAGE_BYTES - ST_WT);
    tma_3d(sb + ST_WT, &m.wt, 80 * hg + (tail_first(hg) ? 0 : 64), 0, 0, bars + 8 * B_FULL1);
    load_stage(sb, 1, b, m);
  } else if (tid == T_INIT) {
#pragma unroll
    for (int i = 0; i < B_F0; i++) mbar_init(bars + 8 * i, i < B_GATE ? 8 : i < B_CVD ? 4 : i == B_CVD ? 20 : 1);
    fence_async_smem();
  }
  const int warp = __shfl_sync(0xffffffffu, tid >> 5, 0), wg = warp >> 2, w = warp & 3;
  __syncthreads();

  if (wg == 3) {
    asm volatile("setmaxnreg.dec.sync.aligned.u32 56;");
    if (w == 0) {
      if (lane == 0) {
#pragma unroll 1
        for (int kb = 2; kb < 10; kb++) {
          if (kb >= 4) mbar_wait(bars + 8 * (kb == 7 ? B_E3 : B_EMPTY1 + (kb & 3)), (kb >> 3) & 1);
          TSIF(kb >= 4, 44 + kb);
          load_stage(sb, kb, b, m);
          TSIF(kb == 3, 60);
          if (kb == TRIG_KB) mbar_arrive(bars + 8 * B_LAST);
        }
        mbar_wait(bars + 8 * B_WOP, 0);
        mbar_wait(bars + 8 * WL_TRIG, 0);
        mbar_wait(bars + 8 * B_EPOCH, 0);
        flag_wait(g_cnt + C_W + 32 * hg, (lds32(sb + OFF_EPOCH) + 1) * 16);
        TS(30);
#pragma unroll 1
        for (int j = 0; j < 8; j++) {
          if (j >= 6) mbar_wait(bars + 8 * (B_EMPTY2 + j - 6), 0);
          if (j == 4) mbar_wait(bars + 8 * (RB32 & 2 ? B_ORB : B_ATTN), 0);
          TSIF(j >= 6, 100 + j);
          mbar_expect_tx(bars + 8 * (B_FULL2 + j), j == 0 ? WO_BYTES : j == 5 ? O_BYTES + WO_BYTES + 512 : O_BYTES + WO_BYTES);
          bulk_load(sb + off_w(j), g_WO + (hg * 8 + step_src(hg, j)) * 800, WO_BYTES, bars + 8 * (B_FULL2 + j));
        }
        mbar_wait(bars + 8 * (B_EMPTY2 + 3), 0);
        mbar_expect_tx(bars + 8 * B_QF, O_BYTES);
        tma_2d(sb + OFF_QS, &m.qm, 80 * hg, 128 * r, bars + 8 * B_QF);
        tma_2d(sb + OFF_QT, &m.qt, 80 * hg + 64, 128 * r, bars + 8 * B_QF);
      }
    } else if (w == 1) {
      unsigned epoch = 0;
      if (lane == 0) {
        epoch = atomicAdd(g_cnt + C_LAUNCH, 1u) / NCTA;
        asm volatile("st.shared.u32 [%0], %1;" ::"r"(sb + OFF_EPOCH), "r"(epoch) : "memory");
        mbar_arrive(bars + 8 * B_EPOCH);
        mbar_wait(bars + 8 * B_KVD, 0);
        mbar_expect_tx(bars + 8 * B_HB, 5 * 4096);
#pragma unroll 1
        for (int c = 0; c < 5; c++) {
          if (c == 3) mbar_wait(bars + 8 * B_S3, 0);
          bulk_load(sb + off_ch(c) + U_BYTES, p.ssm_k + (5 * b + c) * SEQ, 4096, bars + 8 * B_HB);
        }
#pragma unroll
        for (int c = 0; c < 4; c++) mbar_expect_tx(bars + 8 * (B_U + c), c < 3 ? U_BYTES : 2 * U_BYTES);
        const uint4* usrc = g_U + 5 * b * U_PITCH;
        mbar_wait(bars + 8 * B_USIG, 0);
        flag_wait(g_cnt + C_PREP + 32 * (b & 15), (epoch + 1) * NCTA);
        TS(23);
#pragma unroll
        for (int c = 0; c < 5; c++) {
          if (c == 3) mbar_wait(bars + 8 * (B_U + 2), 0);
          bulk_load(sb + off_ch(c), usrc + c * U_PITCH, U_BYTES, bars + 8 * (B_U + (c < 3 ? c : 3)));
          TSIF(c == 0 || c == 4, 116 + (c >> 2));
        }
      }
      epoch = __shfl_sync(0xffffffffu, epoch, 0);
      if (lane < 8) {
        const int src = (b & ~7) | step_src(hg, lane);
        mbar_wait(bars + 8 * B_ATTN, 0);
        TS(20);
        bool seen = false;
#pragma unroll 1
        for (int spins = 0; spins < SPIN_LIMIT; spins++) {
          const bool now = !seen && (int)(flag_read(g_cnt + C_O + 32 * src) - (epoch + 1)) >= 0;
          if (now && lane >= 1 && lane < 4) bulk_load(sb + off_o(lane), g_O + src * 1280, O_BYTES, bars + 8 * (B_FULL2 + lane));
          seen = seen || now;
          if (__all_sync(0xff, seen)) break;
        }
        TS(21);
        if (lane == 5) bulk_load(sb + OFF_GATE, g_gate + 128 * r, 512, bars + 8 * (B_FULL2 + 5));
#pragma unroll 1
        for (int j = 4; j < 8; j++) {
          if (lane == j) {
            mbar_wait(bars + 8 * (j < 6 ? B_C34 : B_EMPTY2 + j - 6), 0);
            bulk_load(sb + off_o(j), g_O + src * 1280, O_BYTES, bars + 8 * (B_FULL2 + j));
          }
          __syncwarp(0xff);
        }
        TS(22);
      }
    } else if (w == 2) {
      mbar_wait(bars + 8 * B_PREP, 0);
      flag_signal(g_cnt + C_PREP, 16, lane);
      TS(25);
      if (lane == 0) {
        mbar_arrive(bars + 8 * B_USIG);
        mbar_expect_tx(bars + 8 * B_ORB, (RB32 & 2 ? O_BYTES / 4 : O_BYTES) + 64);
        mbar_wait(bars + 8 * B_GATE, 0);
        publish(g_gate + 16 * b, sb + OFF_GATE + 64 * hg, 64, bars + 8 * B_ORB);
        mbar_wait(bars + 8 * B_ATTN, 0);
        if (RB32 & 2) {
          bulk_store(g_O + b * 1280, sb + OFF_OA, O_BYTES);
          bulk_wait_read();
          tma_2d(sb + OFF_KVX + 10240, &m.ol, 48, b * 160, bars + 8 * B_ORB);
        } else {
          publish(g_O + b * 1280, sb + OFF_OA, O_BYTES, bars + 8 * B_ORB);
        }
        TS(74);
        mbar_wait(bars + 8 * B_ORB, 0);
        flag_bump(g_cnt + C_O + 32 * b);
        TS(26);
        mbar_arrive(bars + 8 * B_OSIG);
      }
    } else {
      if (lane == 0) {
        uint4* dst = g_WO + (hg * 8 + (r >> 1)) * 800 + (r & 1) * 80;
        mbar_wait(bars + 8 * B_S3, 0);
        asm volatile("cp.async.bulk.prefetch.L2.global [%0], 6400;" ::"l"(p.wo + b * 3200) : "memory");
        mbar_wait(bars + 8 * B_P1, 0);
        mbar_wait(bars + 8 * WB_TRIG, 0);
        mbar_expect_tx(bars + 8 * B_WST, WO_BYTES / 2);
        tma_3d(sb + OFF_WA, &m.wo, 0, 40 * r, 5 * hg, bars + 8 * B_WST);
        mbar_wait(bars + 8 * B_WST, 0);
#pragma unroll 1
        for (int n = 0; n < 5; n++) bulk_store(dst + 160 * n, sb + OFF_WA + 1280 * n, 1280);
        bulk_wait_read();
        mbar_expect_tx(bars + 8 * B_WST, WO_BYTES / 2);
#pragma unroll 1
        for (int n = 0; n < 5; n++) bulk_load(sb + OFF_WA + 1280 * n, dst + 160 * n, 1280, bars + 8 * B_WST);
        mbar_wait(bars + 8 * B_WST, 1);
        flag_bump(g_cnt + C_W + 32 * hg);
        mbar_arrive(bars + 8 * B_WOP);
        TS(71);
        mbar_expect_tx(bars + 8 * B_C34, 3 * (RB32 & 1 ? 1024 : U_BYTES));
        mbar_expect_tx(bars + 8 * B_YRB, 2 * (RB32 & 1 ? 1024 : U_BYTES));
#pragma unroll 1
        for (int c = 0; c < 5; c++) {
          mbar_wait(bars + 8 * (B_YST + c), 0);
          if (RB32 & 1) {
            bulk_store(g_U + (5 * b + c) * U_PITCH, sb + off_ch(c), U_BYTES);
            bulk_wait_read();
            tma_2d(sb + off_ch(c), &m.yl, 48, (5 * b + c) * (U_PITCH / 8), bars + 8 * (c < 3 ? B_C34 : B_YRB));
          } else {
            publish(g_U + (5 * b + c) * U_PITCH, sb + off_ch(c), U_BYTES, bars + 8 * (c < 3 ? B_C34 : B_YRB));
          }
        }
        TS(75);
        mbar_wait(bars + 8 * B_C34, 0);
        mbar_wait(bars + 8 * B_YRB, 0);
        flag_bump(g_cnt + C_Y + 32 * (b >> 4));
        TS(27);
        mbar_arrive(bars + 8 * B_YSIG);
        mbar_expect_tx(bars + 8 * B_YFULL, 20480);
        flag_wait(g_cnt + C_Y + 32 * hg, (lds32(sb + OFF_EPOCH) + 1) * 16);
        TS(24);
        tma_2d(sb + OFF_YT, &m.y, 128 * r, 80 * hg, bars + 8 * B_YFULL);
        tma_2d(sb + OFF_YT + 10240, &m.y, 128 * r + 64, 80 * hg, bars + 8 * B_YFULL);
      }
    }
  } else {
    asm volatile("setmaxnreg.inc.sync.aligned.u32 152;");
    if (wg < 2) {
      float acc[120];
#pragma unroll
      for (int i = 0; i < 120; i++) acc[i] = 0.f;
      const uint32_t da = desc_lo(sb + wg * 8192, 16), db = desc_lo(sb + ST_W, 8192), dc = desc_lo(sb + ST_WT, 2048);
      mbar_wait(bars + 8 * B_F0, 0);
      TSIF(w == 0 && wg == 0, 1);
      wg_fence();
#pragma unroll
      for (int k = 0; k < 4; k++) WgSST<192>::mma<HI_SW128, HI_SW128>(acc, da + 2 * k, db + 128 * k, 1);
      wg_commit();
      mbar_wait(bars + 8 * B_FULL1, 0);
      wg_fence();
#pragma unroll
      for (int k = 0; k < 4; k++) WgSST<48>::mma<HI_SW128, HI_SW32>(acc + 96, da + 2 * k, dc + 32 * k, 1);
      wg_commit();
#pragma unroll 1
      for (int kb = 1; kb < 10; kb++) {
        mbar_wait(bars + 8 * (B_FULL1 + (kb & 3)), (kb >> 2) & 1);
        const uint32_t so = (kb & 3) * (STAGE_BYTES >> 4);
        wg_fence();
#pragma unroll
        for (int k = 0; k < 4; k++) {
          WgSST<192>::mma<HI_SW128, HI_SW128>(acc, da + so + 2 * k, db + so + 128 * k, 1);
          WgSST<48>::mma<HI_SW128, HI_SW32>(acc + 96, da + so + 2 * k, dc + so + 32 * k, 1);
        }
        wg_commit();
        wg_wait<1>();
        if (lane == 0) mbar_arrive(bars + 8 * (kb == 4 ? B_E3 : B_EMPTY1 + ((kb - 1) & 3)));
      }
      mbar_wait(bars + 8 * B_EPOCH, 0);
      const uint32_t tag = lds32(sb + OFF_EPOCH) + 1;
      mbar_wait(bars + 8 * B_S3, 0);
      wg_wait<0>();
      pin<120>(acc);
      if (lane == 0) mbar_arrive(bars + 8 * B_P1);
      TSM(w == 0, 3 + wg);
      attention(acc, sb, b, wg, w, lane, tag);
    } else {
      const int tw = tid & 127, chl = 64 * (b & 1) + 8 * w + (lane >> 2);
      uint4* up = g_U + chl * U_PITCH + ((4 * (b >> 1) + (lane & 3)) ^ ((b >> 2) & 1));
      uint2 sw[10];
      uint32_t dv = 0;
      if (lane < 5) dv = __ldg(reinterpret_cast<const unsigned short*>(p.ssm_D) + 5 * b + lane);
#pragma unroll
      for (int i = 0; i < 10; i++) sw[i] = ldg64(reinterpret_cast<const uint2*>(p.shift_k) + chl + 128 * (i >> 1) + 32 * (i & 1));
      uint32_t tab[12];
      uint32_t tt[2];
      fft_tables(tab, tw);
      fft_twiddles(tt, tw);
      uint4 res[10];
#pragma unroll
      for (int i = 0; i < 10; i++) res[i] = make_uint4(0, 0, 0, 0);
#pragma unroll 1
      for (int slab = 0; slab < 5; slab++) {
#pragma unroll
        for (int i = 0; i < 8; i++) res[i] = res[i + 2];
        prep_slab(res + 8, sw, sb, slab, w, lane);
        TSIF(w == 0, 99 + 4 * slab);
#pragma unroll
        for (int i = 0; i < 8; i++) sw[i] = sw[i + 2];
      }
      TSIF(w == 0, 28);
      __syncwarp();
      if (lane == 0) mbar_arrive(bars + 8 * B_KVD + ((res[8].x ^ res[9].x) & p.zero));
      mbar_wait(bars + 8 * B_KVD, 0);
      fft_tables_store(tab, sb, tw);
      mbar_wait(bars + 8 * B_LAST, 0);
#pragma unroll
      for (int i = 0; i < 10; i++) up[(128 * (i >> 1) + 32 * (i & 1)) * U_PITCH] = res[i];
      __syncwarp();
      if (lane == 0) mbar_arrive(bars + 8 * B_PREP);
      TSIF(w == 0, 5);
      mbar_wait(bars + 8 * B_LAST, 0);
      prep_gate(p, sb, b, w, lane);
      __syncwarp();
      if (lane == 0) mbar_arrive(bars + 8 * B_GATE);
      TSIF(w == 0, 72);
      mbar_wait(bars + 8 * B_HB, 0);
      TSIF(w == 0, 2);
      const uint32_t ha = sb + U_BYTES + ((tw >> 3) * 16 + 8 + (tw & 7)) * 16;
      uint4 hv[5];
#pragma unroll
      for (int c = 0; c < 5; c++) hv[c] = lds128(ha + off_ch(c));
      __syncwarp();
#pragma unroll
      for (int c = 0; c < 5; c++) sts128((ha ^ 16) + off_ch(c), hv[c].x, hv[c].y, hv[c].z, hv[c].w);
      asm volatile("st.shared.v2.u32 [%0], {%1, %2};" ::"r"(sb + OFF_TT + 8 * tw), "r"(tt[0]), "r"(tt[1]) : "memory");
      if (tw < 5) asm volatile("st.shared.f32 [%0], %1;" ::"r"(sb + OFF_D + 4 * tw), "f"(bf_lo(dv) * 0.125f) : "memory");
      fence_async_smem();
      __syncwarp();
      if (lane == 0) mbar_arrive(bars + 8 * B_HA);
      TSIF(w == 0, 6);
    }

    FftConst fc;
    TSM(w == 0 && wg == 0, 104);
    mbar_wait(bars + 8 * B_HA, 0);
    fft_matrices(fc, sb, w, lane);
    TSM(w == 0 && wg == 0, 105);
    TSM(w == 0 && wg == 2, 124);
    uint32_t tasks = wg == 0 ? TASK0 : wg == 1 ? TASK1 : TASK2, fa[4][4];
    {
      float X[32];
      wg_fence();
      f_step(X, fc, desc_lo(sb + off_ch((tasks & 7) - 1) + U_BYTES, 1024));
      wg_wait<0>();
      pin<32>(X);
      twiddle_fwd(fa, X, fc);
    }
#pragma unroll 1
    for (; tasks; tasks >>= 4) {
      const int c = (tasks & 7) - 1;
      conv_channel(fc, fa, sb, c, ((tasks >> 4) & 7) - 1, wg, w, lane);
      if (lane == 0) mbar_arrive(bars + 8 * (B_YST + c));
      TSM(w == 0, 10 + c);
    }

    if (wg != WO_SKIP) {
      const int wg = (warp >> 2) > WO_SKIP ? (warp >> 2) - 1 : warp >> 2;
      const int g = lane >> 2;
      float acc[40];
#pragma unroll
      for (int i = 0; i < 40; i++) acc[i] = 0.f;
      const uint32_t da = desc_lo(sb + wg * 1024, 2048), db = desc_lo(sb, 2560);
      mbar_wait(bars + 8 * B_ORB, 0);
      mbar_wait(bars + 8 * B_FULL2, 0);
      mbar_wait(bars + 8 * B_CVD, 0);
      TSM(w == 0, 15 + wg);
#pragma unroll 1
      for (int j = 0; j < 8; j++) {
        mbar_wait(bars + 8 * (B_FULL2 + j), 0);
        TSM(w == 0 && wg == 0, 44 + (j < 4 ? j : j + 6));
        const uint32_t oa = da + (off_o(j) >> 4), ob = db + (off_w(j) >> 4);
        wg_fence();
#pragma unroll
        for (int k = 0; k < 5; k++) WgSST<80>::mma<HI_NONE, HI_SW32>(acc, oa + 256 * k, ob + 32 * k, 1);
        wg_commit();
        wg_wait<1>();
        if (j >= 1 && j <= 4 && lane == 0) mbar_arrive(bars + 8 * (B_EMPTY2 + j - 1));
      }
      TSIF(w == 0 && wg == 0, 113);
      const int tr = 64 * wg + 16 * w + (lane & 15);
      const uint32_t fm = sb + OFF_QS + tr * 128, fx = (lane >> 4) ^ (tr & 7);
      const uint32_t ft = sb + OFF_QT + tr * 32 + (((lane >> 4) ^ (tr >> 2)) & 1) * 16;
      const float g0 = __uint_as_float(lds32(sb + OFF_GATE + (64 * wg + 16 * w + g) * 4));
      const float g1 = __uint_as_float(lds32(sb + OFF_GATE + (64 * wg + 16 * w + 8 + g) * 4));
      const uint32_t ga = pack2(g0, g0), gb = pack2(g1, g1);
      const uint32_t na = pack2(1.f - g0, 1.f - g0), nb = pack2(1.f - g1, 1.f - g1);

      uint32_t qf[20];
      mbar_wait(bars + 8 * B_QF, 0);
      TSM(w == 0 && wg == 0, 99);
#pragma unroll
      for (int j = 0; j < 5; j++) ldsm4(qf + 4 * j, j < 4 ? fm + ((fx ^ (2 * j)) << 4) : ft);
#pragma unroll
      for (int i = 0; i < 20; i++) {
        qf[i] = bmul((i & 1) ? gb : ga, qf[i]);
        asm volatile("" : "+r"(qf[i]));
      }

      wg_wait<0>();
      pin<40>(acc);
      TSM(w == 0, 17 + wg);
      uint32_t pb[20];
#pragma unroll
      for (int j = 0; j < 10; j++) {
        pb[2 * j] = bmul(na, pack2(acc[4 * j], acc[4 * j + 1]));
        pb[2 * j + 1] = bmul(nb, pack2(acc[4 * j + 2], acc[4 * j + 3]));
        asm volatile("" : "+r"(pb[2 * j]), "+r"(pb[2 * j + 1]));
      }
      const uint32_t ya = sb + OFF_YT + wg * 10240 + ((lane >> 4) * 8 + (lane & 7)) * 128 +
                          (((2 * w + (((lane >> 3) & 1) ^ wg)) ^ (lane & 7)) << 4);
      mbar_wait(bars + 8 * B_YFULL, 0);
      TSM(w == 0 && wg == 0, 19);
#pragma unroll
      for (int j = 0; j < 5; j++) {
        uint32_t y[4];
        ldsm4t(y, ya + 2048 * j);
#pragma unroll
        for (int i = 0; i < 4; i++)
          qf[4 * j + i] = bfma(qf[4 * j + i], y[i], pb[4 * j + i]);
      }
#pragma unroll
      for (int j = 0; j < 5; j++) stsm4(j < 4 ? fm + ((fx ^ (2 * j)) << 4) : ft, qf + 4 * j);
      fence_async_smem();
      __syncwarp();
      if (lane == 0) {
        const int row = 64 * wg + 16 * w;
        asm volatile("cp.async.bulk.tensor.2d.global.shared::cta.bulk_group [%0, {%2, %3}], [%1];"
                     ::"l"(&m.om), "r"(sb + OFF_QS + row * 128), "r"(80 * hg), "r"(128 * r + row) : "memory");
        asm volatile("cp.async.bulk.tensor.2d.global.shared::cta.bulk_group [%0, {%2, %3}], [%1];"
                     ::"l"(&m.ot), "r"(sb + OFF_QT + row * 32), "r"(80 * hg + 64), "r"(128 * r + row) : "memory");
        asm volatile("cp.async.bulk.commit_group;\ncp.async.bulk.wait_group.read 0;" ::: "memory");
      }
      TSM(w == 0 || w == 3, 40 + 2 * wg + (w & 1));
    }
  }
}

typedef CUresult (*EncodeFn)(CUtensorMap*, CUtensorMapDataType, cuuint32_t, void*, const cuuint64_t*, const cuuint64_t*,
                             const cuuint32_t*, const cuuint32_t*, CUtensorMapInterleave, CUtensorMapSwizzle,
                             CUtensorMapL2promotion, CUtensorMapFloatOOBfill);

void encode(EncodeFn fn, CUtensorMap* tm, const void* base, int rank, const cuuint64_t* dims, const cuuint64_t* strides,
            const cuuint32_t* box, CUtensorMapSwizzle swz) {
  const cuuint32_t ones[3] = {1, 1, 1};
  fn(tm, CU_TENSOR_MAP_DATA_TYPE_BFLOAT16, rank, const_cast<void*>(base), dims, strides, box, ones,
     CU_TENSOR_MAP_INTERLEAVE_NONE, swz, CU_TENSOR_MAP_L2_PROMOTION_L2_128B, CU_TENSOR_MAP_FLOAT_OOB_FILL_NONE);
}

}

extern "C" void kernel_launch(void* const* d_in, const int* in_sizes, int n_in, void* d_out, int out_size) {
  (void)in_sizes; (void)n_in; (void)out_size;
  Params p;
  p.q = (const __nv_bfloat16*)d_in[0];
  p.k = (const __nv_bfloat16*)d_in[1];
  p.v = (const __nv_bfloat16*)d_in[2];
  p.shift_k = (const __nv_bfloat16*)d_in[3];
  p.ssm_k = (const __nv_bfloat16*)d_in[4];
  p.ssm_D = (const __nv_bfloat16*)d_in[5];
  p.wqkv = (const __nv_bfloat16*)d_in[7];
  p.wo = (const __nv_bfloat16*)d_in[8];
  p.gate_w = (const __nv_bfloat16*)d_in[9];
  p.out = (__nv_bfloat16*)d_out;
  p.zero = 0;

  static EncodeFn fn = nullptr;
  static void *yaddr = nullptr, *oaddr = nullptr;
  if (!fn) {
    cudaDriverEntryPointQueryResult qr;
    void* f = nullptr;
    cudaGetDriverEntryPoint("cuTensorMapEncodeTiled", &f, cudaEnableDefault, &qr);
    fn = (EncodeFn)f;
    cudaGetSymbolAddress(&yaddr, g_U);
    cudaGetSymbolAddress(&oaddr, g_O);
    cudaFuncSetAttribute(fused_kernel, cudaFuncAttributeMaxDynamicSharedMemorySize, SMEM_BYTES);
  }
  Maps m;
  {
    const cuuint64_t dims[3] = {640, 1024, 2}, st[2] = {2560, 1280};
    const cuuint32_t box[3] = {64, 64, 2};
    encode(fn, &m.x, p.q, 3, dims, st, box, CU_TENSOR_MAP_SWIZZLE_128B);
  }
  {
    const cuuint64_t dims[3] = {640, 640, 3}, st[2] = {3840, 1280};
    const cuuint32_t box[3] = {64, 64, 3}, boxt[3] = {16, 64, 3};
    encode(fn, &m.wm, p.wqkv, 3, dims, st, box, CU_TENSOR_MAP_SWIZZLE_128B);
    encode(fn, &m.wt, p.wqkv, 3, dims, st, boxt, CU_TENSOR_MAP_SWIZZLE_32B);
  }
  {
    const cuuint64_t dims[3] = {64, 2048, 10}, st[2] = {1280, 128};
    const cuuint32_t boxk[3] = {64, 35, 1}, boxv[3] = {64, 32, 1};
    encode(fn, &m.k, p.k, 3, dims, st, boxk, CU_TENSOR_MAP_SWIZZLE_128B);
    encode(fn, &m.v, p.v, 3, dims, st, boxv, CU_TENSOR_MAP_SWIZZLE_128B);
  }
  {
    const cuuint64_t dims[3] = {16, 640, 40}, st[2] = {1280, 32};
    const cuuint32_t box[3] = {16, 40, 5};
    encode(fn, &m.wo, p.wo, 3, dims, st, box, CU_TENSOR_MAP_SWIZZLE_32B);
  }
  {
    const cuuint64_t dims[2] = {2048, 640}, st[1] = {U_PITCH * 16};
    const cuuint32_t box[2] = {64, 80};
    encode(fn, &m.y, yaddr, 2, dims, st, box, CU_TENSOR_MAP_SWIZZLE_128B);
    const cuuint64_t dl[2] = {64, DIM * U_PITCH / 8}, dol[2] = {64, NCTA * 160}, sl[1] = {128};
    const cuuint32_t bl[2] = {16, 32}, bol[2] = {16, 160};
    encode(fn, &m.yl, yaddr, 2, dl, sl, bl, CU_TENSOR_MAP_SWIZZLE_NONE);
    encode(fn, &m.ol, oaddr, 2, dol, sl, bol, CU_TENSOR_MAP_SWIZZLE_NONE);
  }
  {
    const cuuint64_t dims[2] = {640, 2048}, st[1] = {1280};
    const cuuint32_t bqm[2] = {64, 128}, bqt[2] = {16, 128}, bom[2] = {64, 16}, bot[2] = {16, 16};
    encode(fn, &m.qm, p.q, 2, dims, st, bqm, CU_TENSOR_MAP_SWIZZLE_128B);
    encode(fn, &m.qt, p.q, 2, dims, st, bqt, CU_TENSOR_MAP_SWIZZLE_32B);
    encode(fn, &m.om, p.out, 2, dims, st, bom, CU_TENSOR_MAP_SWIZZLE_128B);
    encode(fn, &m.ot, p.out, 2, dims, st, bot, CU_TENSOR_MAP_SWIZZLE_32B);
  }
  fused_kernel<<<NCTA, NTHR, SMEM_BYTES>>>(m, p);
}
```

```cpp
#include <cuda.h>
#include <cuda_bf16.h>
#include <cuda_runtime.h>
#include <stdint.h>

namespace {

constexpr int SEQ = 2048, DIM = 640, NCTA = 128, NTHR = 512;

#define TRIG_KB 9
#define KV_KB 2
#define DEV_EXIT 0
#define FENCE_LO 0
#define FENCE_HI 0
#define WB_TRIG B_USIG
#define T_ISSUE 256
#define RB32 3
#define WO_SKIP 1
#define Y_EARLY 1
#define T_INIT 448
#define TASK0 0x3
#define TASK1 0x52
#define TASK2 0x41
#define WL_TRIG B_WOP

constexpr uint32_t STAGE_BYTES = 47104, ST_W = 16384, ST_WT = 40960;
constexpr uint32_t O_BYTES = 20480, WO_BYTES = 12800;
constexpr uint32_t OFF_OA = 0;
constexpr uint32_t OFF_QS = 3 * O_BYTES, OFF_QT = OFF_QS + 16384;
constexpr uint32_t OFF_WC = 81920;
constexpr uint32_t OFF_WA = 94720;
constexpr uint32_t OFF_GATE = 145920;
constexpr uint32_t OFF_TT = 146432;
constexpr uint32_t OFF_KVX = 148480;
constexpr uint32_t OFF_CH3 = 163840;
constexpr uint32_t CH_BYTES = 12288, U_BYTES = 4096;
constexpr uint32_t OFF_FT = 225280, OFF_GT = 229376;
constexpr uint32_t OFF_CH0 = 188416;
constexpr uint32_t OFF_KVS = OFF_CH0, KVS_V = 4480, KVS_BYTES = 8576;
constexpr uint32_t OFF_YT = 163840;
constexpr uint32_t OFF_BAR = 231936;
constexpr uint32_t SMEM_BYTES = OFF_BAR + 512;

enum : uint32_t {
  B_EMPTY1 = 0, B_S3 = 3, B_E3 = 4, B_EMPTY2 = 5, B_ATTN = 9, B_P1 = 10,
  B_GATE = 11, B_HA = 12, B_KVD = 13, B_PREP = 14, B_YST = 15,
  B_CVD = 20,
  B_FULL2 = 21, B_U = 29, B_KV = 33, B_HB = 38, B_C34 = 39, B_YRB = 40, B_YFULL = 41, B_EPOCH = 42, B_LAST = 43, B_OSIG = 44,
  B_WOP = 45, B_USIG = 46, B_WST = 47, B_QF = 48, B_ORB = 49, B_YSIG = 50,
  B_F0 = 51, B_FULL1 = 52
};
constexpr uint32_t OFF_EPOCH = OFF_BAR + 8 * 58, OFF_D = OFF_BAR + 8 * 60;
__device__ __forceinline__ uint32_t off_o(int j) { return j < 4 ? OFF_OA + j * O_BYTES : j < 6 ? OFF_CH0 + (j - 4) * O_BYTES : OFF_OA + (j - 6) * O_BYTES; }
__device__ __forceinline__ uint32_t off_w(int j) { return j < 4 ? OFF_WA + j * WO_BYTES : j == 4 ? OFF_KVX : j == 5 ? OFF_WC : OFF_WA + (j - 6) * WO_BYTES; }
__device__ __forceinline__ int step_src(int hg, int j) { return j == 0 ? hg : j <= hg ? j - 1 : j; }
__device__ __forceinline__ bool tail_first(int hg) { return (hg & 3) == 3; }
__device__ __forceinline__ uint32_t off_ch(int c) { return (c < 3 ? OFF_CH0 : OFF_CH3 - 3 * CH_BYTES) + c * CH_BYTES; }

#define U_PITCH 264
__device__ __align__(1024) uint4 g_U[DIM * U_PITCH];
__device__ __align__(128) uint4 g_O[NCTA * 1280];
__device__ uint4 g_WO[64 * 800];
__device__ uint4 g_halo[NCTA * 2 * 7 * 32];
__device__ __align__(128) float g_gate[SEQ];
__device__ unsigned g_cnt[32 * (1 + 2 * 16 + 8 + NCTA)];
constexpr int C_LAUNCH = 0, C_PREP = 32, C_Y = 32 * 17, C_W = 32 * 33, C_O = 32 * 41;

#define TSM(cond, slot) do { } while (0)
#define TSIF(cond, slot) do { if (__LINE__ >= FENCE_LO && __LINE__ < FENCE_HI) sched_fence(); } while (0)
__device__ __forceinline__ void sched_fence() {
  asm volatile("{\n.reg .pred p;\n.reg .u32 c;\nmov.u32 c, %%clock;\nsetp.eq.u32 p, c, 0;\n@p st.shared.u32 [%0], c;\n}"
               ::"r"(1024 + OFF_EPOCH + 4) : "memory");
}
#define TS(slot) TSIF(true, slot)

struct Params {
  const __nv_bfloat16 *q, *k, *v, *shift_k, *ssm_k, *ssm_D, *wqkv, *wo, *gate_w;
  __nv_bfloat16* out;
  uint32_t zero;
};

constexpr int SPIN_LIMIT = 1 << 17;

__device__ __forceinline__ void mbar_init(uint32_t bar, uint32_t count) {
  asm volatile("mbarrier.init.shared::cta.b64 [%0], %1;" ::"r"(bar), "r"(count) : "memory");
}
__device__ __forceinline__ void mbar_expect_tx(uint32_t bar, uint32_t bytes) {
  asm volatile("mbarrier.arrive.expect_tx.shared::cta.b64 _, [%0], %1;" ::"r"(bar), "r"(bytes) : "memory");
}
__device__ __forceinline__ void mbar_arrive(uint32_t bar) {
  asm volatile("mbarrier.arrive.shared::cta.b64 _, [%0];" ::"r"(bar) : "memory");
}
__device__ __forceinline__ void mbar_wait(uint32_t bar, uint32_t parity) {
  uint32_t ok;
  int spins = 0;
  do {
      asm volatile("{\n.reg .pred p;\nmbarrier.try_wait.parity.shared::cta.b64 p, [%1], %2;\nselp.b32 %0, 1, 0, p;\n}"
                   : "=r"(ok) : "r"(bar), "r"(parity) : "memory");
    if (++spins > SPIN_LIMIT) break;
  } while (!ok);
}
__device__ __forceinline__ unsigned flag_read(const unsigned* p) {
  unsigned v;
  asm volatile("ld.relaxed.gpu.global.u32 %0, [%1];" : "=r"(v) : "l"(p) : "memory");
  return v;
}
__device__ __forceinline__ void flag_poll(const unsigned* p, unsigned target) {
  unsigned v;
  int spins = 0;
  do {
    asm volatile("ld.relaxed.gpu.global.u32 %0, [%1];" : "=r"(v) : "l"(p) : "memory");
    if (++spins > SPIN_LIMIT) break;
  } while ((int)(v - target) < 0);
}
__device__ __forceinline__ void flag_wait(const unsigned* p, unsigned target) {
  flag_poll(p, target);
}
__device__ __forceinline__ void flag_signal(unsigned* p, int n, int lane) {
  if (lane == 0) asm volatile("fence.release.gpu;" ::: "memory");
  __syncwarp();
  if (lane < n) asm volatile("red.relaxed.gpu.global.add.u32 [%0], 1;" ::"l"(p + 32 * lane) : "memory");
}
__device__ __forceinline__ void flag_bump(unsigned* p) {
  asm volatile("red.relaxed.gpu.global.add.u32 [%0], 1;" ::"l"(p) : "memory");
}
__device__ __forceinline__ void fence_async_smem() { asm volatile("fence.proxy.async.shared::cta;" ::: "memory"); }
__device__ __forceinline__ void wg_sync(int id) { asm volatile("bar.sync %0, 128;" ::"r"(id) : "memory"); }

__device__ __forceinline__ void tma_2d(uint32_t dst, const CUtensorMap* tm, int c0, int c1, uint32_t bar) {
  asm volatile("cp.async.bulk.tensor.2d.shared::cluster.global.mbarrier::complete_tx::bytes [%0], [%1, {%3, %4}], [%2];"
               ::"r"(dst), "l"(tm), "r"(bar), "r"(c0), "r"(c1) : "memory");
}
__device__ __forceinline__ void tma_3d(uint32_t dst, const CUtensorMap* tm, int c0, int c1, int c2, uint32_t bar) {
  asm volatile("cp.async.bulk.tensor.3d.shared::cluster.global.mbarrier::complete_tx::bytes [%0], [%1, {%3, %4, %5}], [%2];"
               ::"r"(dst), "l"(tm), "r"(bar), "r"(c0), "r"(c1), "r"(c2) : "memory");
}
__device__ __forceinline__ void bulk_load(uint32_t dst, const void* src, uint32_t bytes, uint32_t bar) {
  asm volatile("cp.async.bulk.shared::cluster.global.mbarrier::complete_tx::bytes [%0], [%1], %2, [%3];"
               ::"r"(dst), "l"(src), "r"(bytes), "r"(bar) : "memory");
}
__device__ __forceinline__ void bulk_store(void* dst, uint32_t src, uint32_t bytes) {
  asm volatile("cp.async.bulk.global.shared::cta.bulk_group [%0], [%1], %2;" ::"l"(dst), "r"(src), "r"(bytes) : "memory");
}
__device__ __forceinline__ void bulk_wait_read() {
  asm volatile("cp.async.bulk.commit_group;\ncp.async.bulk.wait_group.read 0;" ::: "memory");
}

__device__ __forceinline__ void publish(void* dst, uint32_t src, uint32_t bytes, uint32_t bar) {
  bulk_store(dst, src, bytes);
  bulk_wait_read();
  bulk_load(src, dst, bytes, bar);
}

__device__ __forceinline__ void wg_fence() { asm volatile("wgmma.fence.sync.aligned;" ::: "memory"); }
__device__ __forceinline__ void wg_commit() { asm volatile("wgmma.commit_group.sync.aligned;" ::: "memory"); }
template <int N> __device__ __forceinline__ void wg_wait() { asm volatile("wgmma.wait_group.sync.aligned %0;" ::"n"(N) : "memory"); }
__device__ __forceinline__ uint32_t desc_lo(uint32_t addr, uint32_t lbo) { return ((addr & 0x3FFFF) >> 4) | ((lbo >> 4) << 16); }
constexpr uint32_t desc_hi(uint32_t sbo, uint32_t swz) { return (sbo >> 4) | (swz << 30); }
constexpr uint32_t HI_SW128 = desc_hi(1024, 1), HI_SW64 = desc_hi(512, 2), HI_SW32 = desc_hi(256, 3), HI_NONE = desc_hi(128, 0);
template <int N> __device__ __forceinline__ void pin(float* d) {
#pragma unroll
  for (int i = 0; i < N; i++) asm volatile("" : "+f"(d[i])::"memory");
}

__device__ __forceinline__ uint32_t lds32(uint32_t a) {
  uint32_t v;
  asm volatile("ld.volatile.shared.u32 %0, [%1];" : "=r"(v) : "r"(a) : "memory");
  return v;
}
__device__ __forceinline__ uint2 ldg64(const void* a) {
  uint2 v;
  asm volatile("ld.global.nc.v2.u32 {%0, %1}, [%2];" : "=r"(v.x), "=r"(v.y) : "l"(a) : "memory");
  return v;
}
__device__ __forceinline__ void ldsm4(uint32_t* r, uint32_t a) {
  asm volatile("ldmatrix.sync.aligned.m8n8.x4.shared.b16 {%0, %1, %2, %3}, [%4];"
               : "=r"(r[0]), "=r"(r[1]), "=r"(r[2]), "=r"(r[3]) : "r"(a) : "memory");
}
__device__ __forceinline__ void ldsm4t(uint32_t* r, uint32_t a) {
  asm volatile("ldmatrix.sync.aligned.m8n8.x4.trans.shared.b16 {%0, %1, %2, %3}, [%4];"
               : "=r"(r[0]), "=r"(r[1]), "=r"(r[2]), "=r"(r[3]) : "r"(a) : "memory");
}
__device__ __forceinline__ uint2 lds64(uint32_t a) {
  uint2 v;
  asm volatile("ld.shared.v2.u32 {%0, %1}, [%2];" : "=r"(v.x), "=r"(v.y) : "r"(a) : "memory");
  return v;
}
__device__ __forceinline__ uint4 lds128(uint32_t a) {
  uint4 v;
  asm volatile("ld.shared.v4.u32 {%0, %1, %2, %3}, [%4];" : "=r"(v.x), "=r"(v.y), "=r"(v.z), "=r"(v.w) : "r"(a) : "memory");
  return v;
}
__device__ __forceinline__ void sts128(uint32_t a, uint32_t x, uint32_t y, uint32_t z, uint32_t w) {
  asm volatile("st.shared.v4.u32 [%0], {%1, %2, %3, %4};" ::"r"(a), "r"(x), "r"(y), "r"(z), "r"(w) : "memory");
}
__device__ __forceinline__ void stsm4(uint32_t a, const uint32_t* r) {
  asm volatile("stmatrix.sync.aligned.m8n8.x4.shared.b16 [%0], {%1, %2, %3, %4};" ::"r"(a), "r"(r[0]), "r"(r[1]), "r"(r[2]), "r"(r[3]) : "memory");
}
__device__ __forceinline__ uint32_t pack2(float lo, float hi) {
  uint32_t r;
  asm("cvt.rn.bf16x2.f32 %0, %1, %2;" : "=r"(r) : "f"(hi), "f"(lo));
  return r;
}
__device__ __forceinline__ uint32_t movm(uint32_t a) {
  uint32_t d;
  asm volatile("movmatrix.sync.aligned.m8n8.trans.b16 %0, %1;" : "=r"(d) : "r"(a));
  return d;
}
__device__ __forceinline__ uint32_t bmul(uint32_t a, uint32_t b) {
  uint32_t d;
  asm("mul.rn.bf16x2 %0, %1, %2;" : "=r"(d) : "r"(a), "r"(b));
  return d;
}
__device__ __forceinline__ uint32_t badd(uint32_t a, uint32_t b) {
  uint32_t d;
  asm("add.rn.bf16x2 %0, %1, %2;" : "=r"(d) : "r"(a), "r"(b));
  return d;
}
__device__ __forceinline__ uint32_t bfma(uint32_t a, uint32_t b, uint32_t c) {
  uint32_t d;
  asm("fma.rn.bf16x2 %0, %1, %2, %3;" : "=r"(d) : "r"(a), "r"(b), "r"(c));
  return d;
}
__device__ __forceinline__ float bf_lo(uint32_t x) { return __uint_as_float(x << 16); }
__device__ __forceinline__ float bf_hi(uint32_t x) { return __uint_as_float(x & 0xFFFF0000u); }
__device__ __forceinline__ float ex2(float x) {
  float y;
  asm("ex2.approx.ftz.f32 %0, %1;" : "=f"(y) : "f"(x));
  return y;
}
__device__ __forceinline__ float rcp(float x) {
  float y;
  asm("rcp.approx.ftz.f32 %0, %1;" : "=f"(y) : "f"(x));
  return y;
}
__device__ __forceinline__ void mma16816(float* d, uint32_t a0, uint32_t a1, uint32_t a2, uint32_t a3, uint32_t b0, uint32_t b1) {
  asm volatile("mma.sync.aligned.m16n8k16.row.col.f32.bf16.bf16.f32 {%0, %1, %2, %3}, {%4, %5, %6, %7}, {%8, %9}, {%0, %1, %2, %3};"
               : "+f"(d[0]), "+f"(d[1]), "+f"(d[2]), "+f"(d[3])
               : "r"(a0), "r"(a1), "r"(a2), "r"(a3), "r"(b0), "r"(b1));
}
__device__ __forceinline__ void mma1688(float* d, uint32_t a0, uint32_t a1, uint32_t b0) {
  asm volatile("mma.sync.aligned.m16n8k8.row.col.f32.bf16.bf16.f32 {%0, %1, %2, %3}, {%4, %5}, {%6}, {%0, %1, %2, %3};"
               : "+f"(d[0]), "+f"(d[1]), "+f"(d[2]), "+f"(d[3])
               : "r"(a0), "r"(a1), "r"(b0));
}

template <int N> struct WgRS;
template <int N> struct WgSST;
template <> struct WgRS<32> {
  template <uint32_t HB>
  static __device__ __forceinline__ void mma(float* d, const uint32_t* a, uint32_t db) {
    asm volatile("{\n.reg .pred p;\n.reg .b64 db;\nsetp.ne.b32 p, %22, 0;\n"
      "mov.b64 db, {%20, %21};\n"
      "wgmma.mma_async.sync.aligned.m64n32k16.f32.bf16.bf16 {"
      "%0, %1, %2, %3, %4, %5, %6, %7, %8, %9, %10, %11, %12, %13, %14, %15"
      "}, {%16, %17, %18, %19}, db, p, 1, 1, 1;\n}\n"
      : "+f"(d[0]), "+f"(d[1]), "+f"(d[2]), "+f"(d[3]), "+f"(d[4]), "+f"(d[5]), "+f"(d[6]), "+f"(d[7]),
        "+f"(d[8]), "+f"(d[9]), "+f"(d[10]), "+f"(d[11]), "+f"(d[12]), "+f"(d[13]), "+f"(d[14]), "+f"(d[15])
      : "r"(a[0]), "r"(a[1]), "r"(a[2]), "r"(a[3]), "r"(db), "n"(HB), "n"(1));
  }
  template <uint32_t HB>
  static __device__ __forceinline__ void set(float* d, const uint32_t* a, uint32_t db) {
    asm volatile("{\n.reg .pred p;\n.reg .b64 db;\nsetp.ne.b32 p, %22, 0;\n"
      "mov.b64 db, {%20, %21};\n"
      "wgmma.mma_async.sync.aligned.m64n32k16.f32.bf16.bf16 {"
      "%0, %1, %2, %3, %4, %5, %6, %7, %8, %9, %10, %11, %12, %13, %14, %15"
      "}, {%16, %17, %18, %19}, db, p, 1, 1, 1;\n}\n"
      : "=f"(d[0]), "=f"(d[1]), "=f"(d[2]), "=f"(d[3]), "=f"(d[4]), "=f"(d[5]), "=f"(d[6]), "=f"(d[7]),
        "=f"(d[8]), "=f"(d[9]), "=f"(d[10]), "=f"(d[11]), "=f"(d[12]), "=f"(d[13]), "=f"(d[14]), "=f"(d[15])
      : "r"(a[0]), "r"(a[1]), "r"(a[2]), "r"(a[3]), "r"(db), "n"(HB), "n"(0));
  }
};
template <> struct WgRS<64> {
  template <uint32_t HB>
  static __device__ __forceinline__ void mma(float* d, const uint32_t* a, uint32_t db) {
    asm volatile("{\n.reg .pred p;\n.reg .b64 db;\nsetp.ne.b32 p, %38, 0;\n"
      "mov.b64 db, {%36, %37};\n"
      "wgmma.mma_async.sync.aligned.m64n64k16.f32.bf16.bf16 {"
      "%0, %1, %2, %3, %4, %5, %6, %7, %8, %9, %10, %11, %12, %13, %14, %15, "
      "%16, %17, %18, %19, %20, %21, %22, %23, %24, %25, %26, %27, %28, %29, %30, %31"
      "}, {%32, %33, %34, %35}, db, p, 1, 1, 1;\n}\n"
      : "+f"(d[0]), "+f"(d[1]), "+f"(d[2]), "+f"(d[3]), "+f"(d[4]), "+f"(d[5]), "+f"(d[6]), "+f"(d[7]),
        "+f"(d[8]), "+f"(d[9]), "+f"(d[10]), "+f"(d[11]), "+f"(d[12]), "+f"(d[13]), "+f"(d[14]), "+f"(d[15]),
        "+f"(d[16]), "+f"(d[17]), "+f"(d[18]), "+f"(d[19]), "+f"(d[20]), "+f"(d[21]), "+f"(d[22]), "+f"(d[23]),
        "+f"(d[24]), "+f"(d[25]), "+f"(d[26]), "+f"(d[27]), "+f"(d[28]), "+f"(d[29]), "+f"(d[30]), "+f"(d[31])
      : "r"(a[0]), "r"(a[1]), "r"(a[2]), "r"(a[3]), "r"(db), "n"(HB), "n"(1));
  }
  template <uint32_t HB>
  static __device__ __forceinline__ void set(float* d, const uint32_t* a, uint32_t db) {
    asm volatile("{\n.reg .pred p;\n.reg .b64 db;\nsetp.ne.b32 p, %38, 0;\n"
      "mov.b64 db, {%36, %37};\n"
      "wgmma.mma_async.sync.aligned.m64n64k16.f32.bf16.bf16 {"
      "%0, %1, %2, %3, %4, %5, %6, %7, %8, %9, %10, %11, %12, %13, %14, %15, "
      "%16, %17, %18, %19, %20, %21, %22, %23, %24, %25, %26, %27, %28, %29, %30, %31"
      "}, {%32, %33, %34, %35}, db, p, 1, 1, 1;\n}\n"
      : "=f"(d[0]), "=f"(d[1]), "=f"(d[2]), "=f"(d[3]), "=f"(d[4]), "=f"(d[5]), "=f"(d[6]), "=f"(d[7]),
        "=f"(d[8]), "=f"(d[9]), "=f"(d[10]), "=f"(d[11]), "=f"(d[12]), "=f"(d[13]), "=f"(d[14]), "=f"(d[15]),
        "=f"(d[16]), "=f"(d[17]), "=f"(d[18]), "=f"(d[19]), "=f"(d[20]), "=f"(d[21]), "=f"(d[22]), "=f"(d[23]),
        "=f"(d[24]), "=f"(d[25]), "=f"(d[26]), "=f"(d[27]), "=f"(d[28]), "=f"(d[29]), "=f"(d[30]), "=f"(d[31])
      : "r"(a[0]), "r"(a[1]), "r"(a[2]), "r"(a[3]), "r"(db), "n"(HB), "n"(0));
  }
};
template <> struct WgSST<48> {
  template <uint32_t HA, uint32_t HB>
  static __device__ __forceinline__ void mma(float* d, uint32_t da, uint32_t db, int sc) {
    asm volatile("{\n.reg .pred p;\n.reg .b64 da, db;\nsetp.ne.b32 p, %28, 0;\n"
      "mov.b64 da, {%24, %25};\nmov.b64 db, {%26, %27};\n"
      "wgmma.mma_async.sync.aligned.m64n48k16.f32.bf16.bf16 {"
      "%0, %1, %2, %3, %4, %5, %6, %7, %8, %9, %10, %11, %12, %13, %14, %15, "
      "%16, %17, %18, %19, %20, %21, %22, %23"
      "}, da, db, p, 1, 1, 0, 1;\n}\n"
      : "+f"(d[0]), "+f"(d[1]), "+f"(d[2]), "+f"(d[3]), "+f"(d[4]), "+f"(d[5]), "+f"(d[6]), "+f"(d[7]),
        "+f"(d[8]), "+f"(d[9]), "+f"(d[10]), "+f"(d[11]), "+f"(d[12]), "+f"(d[13]), "+f"(d[14]), "+f"(d[15]),
        "+f"(d[16]), "+f"(d[17]), "+f"(d[18]), "+f"(d[19]), "+f"(d[20]), "+f"(d[21]), "+f"(d[22]), "+f"(d[23])
      : "r"(da), "n"(HA), "r"(db), "n"(HB), "r"(sc));
  }
};
template <> struct WgSST<80> {
  template <uint32_t HA, uint32_t HB>
  static __device__ __forceinline__ void mma(float* d, uint32_t da, uint32_t db, int sc) {
    asm volatile("{\n.reg .pred p;\n.reg .b64 da, db;\nsetp.ne.b32 p, %44, 0;\n"
      "mov.b64 da, {%40, %41};\nmov.b64 db, {%42, %43};\n"
      "wgmma.mma_async.sync.aligned.m64n80k16.f32.bf16.bf16 {"
      "%0, %1, %2, %3, %4, %5, %6, %7, %8, %9, %10, %11, %12, %13, %14, %15, "
      "%16, %17, %18, %19, %20, %21, %22, %23, %24, %25, %26, %27, %28, %29, %30, %31, "
      "%32, %33, %34, %35, %36, %37, %38, %39"
      "}, da, db, p, 1, 1, 0, 1;\n}\n"
      : "+f"(d[0]), "+f"(d[1]), "+f"(d[2]), "+f"(d[3]), "+f"(d[4]), "+f"(d[5]), "+f"(d[6]), "+f"(d[7]),
        "+f"(d[8]), "+f"(d[9]), "+f"(d[10]), "+f"(d[11]), "+f"(d[12]), "+f"(d[13]), "+f"(d[14]), "+f"(d[15]),
        "+f"(d[16]), "+f"(d[17]), "+f"(d[18]), "+f"(d[19]), "+f"(d[20]), "+f"(d[21]), "+f"(d[22]), "+f"(d[23]),
        "+f"(d[24]), "+f"(d[25]), "+f"(d[26]), "+f"(d[27]), "+f"(d[28]), "+f"(d[29]), "+f"(d[30]), "+f"(d[31]),
        "+f"(d[32]), "+f"(d[33]), "+f"(d[34]), "+f"(d[35]), "+f"(d[36]), "+f"(d[37]), "+f"(d[38]), "+f"(d[39])
      : "r"(da), "n"(HA), "r"(db), "n"(HB), "r"(sc));
  }
};
template <> struct WgSST<192> {
  template <uint32_t HA, uint32_t HB>
  static __device__ __forceinline__ void mma(float* d, uint32_t da, uint32_t db, int sc) {
    asm volatile("{\n.reg .pred p;\n.reg .b64 da, db;\nsetp.ne.b32 p, %100, 0;\n"
      "mov.b64 da, {%96, %97};\nmov.b64 db, {%98, %99};\n"
      "wgmma.mma_async.sync.aligned.m64n192k16.f32.bf16.bf16 {"
      "%0, %1, %2, %3, %4, %5, %6, %7, %8, %9, %10, %11, %12, %13, %14, %15, "
      "%16, %17, %18, %19, %20, %21, %22, %23, %24, %25, %26, %27, %28, %29, %30, %31, "
      "%32, %33, %34, %35, %36, %37, %38, %39, %40, %41, %42, %43, %44, %45, %46, %47, "
      "%48, %49, %50, %51, %52, %53, %54, %55, %56, %57, %58, %59, %60, %61, %62, %63, "
      "%64, %65, %66, %67, %68, %69, %70, %71, %72, %73, %74, %75, %76, %77, %78, %79, "
      "%80, %81, %82, %83, %84, %85, %86, %87, %88, %89, %90, %91, %92, %93, %94, %95"
      "}, da, db, p, 1, 1, 0, 1;\n}\n"
      : "+f"(d[0]), "+f"(d[1]), "+f"(d[2]), "+f"(d[3]), "+f"(d[4]), "+f"(d[5]), "+f"(d[6]), "+f"(d[7]),
        "+f"(d[8]), "+f"(d[9]), "+f"(d[10]), "+f"(d[11]), "+f"(d[12]), "+f"(d[13]), "+f"(d[14]), "+f"(d[15]),
        "+f"(d[16]), "+f"(d[17]), "+f"(d[18]), "+f"(d[19]), "+f"(d[20]), "+f"(d[21]), "+f"(d[22]), "+f"(d[23]),
        "+f"(d[24]), "+f"(d[25]), "+f"(d[26]), "+f"(d[27]), "+f"(d[28]), "+f"(d[29]), "+f"(d[30]), "+f"(d[31]),
        "+f"(d[32]), "+f"(d[33]), "+f"(d[34]), "+f"(d[35]), "+f"(d[36]), "+f"(d[37]), "+f"(d[38]), "+f"(d[39]),
        "+f"(d[40]), "+f"(d[41]), "+f"(d[42]), "+f"(d[43]), "+f"(d[44]), "+f"(d[45]), "+f"(d[46]), "+f"(d[47]),
        "+f"(d[48]), "+f"(d[49]), "+f"(d[50]), "+f"(d[51]), "+f"(d[52]), "+f"(d[53]), "+f"(d[54]), "+f"(d[55]),
        "+f"(d[56]), "+f"(d[57]), "+f"(d[58]), "+f"(d[59]), "+f"(d[60]), "+f"(d[61]), "+f"(d[62]), "+f"(d[63]),
        "+f"(d[64]), "+f"(d[65]), "+f"(d[66]), "+f"(d[67]), "+f"(d[68]), "+f"(d[69]), "+f"(d[70]), "+f"(d[71]),
        "+f"(d[72]), "+f"(d[73]), "+f"(d[74]), "+f"(d[75]), "+f"(d[76]), "+f"(d[77]), "+f"(d[78]), "+f"(d[79]),
        "+f"(d[80]), "+f"(d[81]), "+f"(d[82]), "+f"(d[83]), "+f"(d[84]), "+f"(d[85]), "+f"(d[86]), "+f"(d[87]),
        "+f"(d[88]), "+f"(d[89]), "+f"(d[90]), "+f"(d[91]), "+f"(d[92]), "+f"(d[93]), "+f"(d[94]), "+f"(d[95])
      : "r"(da), "n"(HA), "r"(db), "n"(HB), "r"(sc));
  }
};

struct FftConst {
  uint32_t f[2][4], fi[4][4];
  uint32_t ta[2][2], tb[2][2];
};
__device__ __forceinline__ void cis(int m, float scale, float& c, float& s) {
  const float a = (float)m * (-6.283185307179586f * scale);
  c = __cosf(a);
  s = __sinf(a);
}
__device__ __forceinline__ void fft_tables(uint32_t (&v)[12], int tw) {
  const int row = tw >> 2, ch = tw & 3;
#pragma unroll
  for (int i = 0; i < 4; i++) {
    float c[2], s[2], x[2];
#pragma unroll
    for (int e = 0; e < 2; e++) {
      cis((((32 * (8 * ch + 2 * i + e) + 15) * (4 * row - 63) + 2048) & 4095) - 2048, 1.f / 4096, c[e], s[e]);
      float gc, gs;
      cis((((row & 15) * (8 * (ch & 1) + 2 * i + e) + 8) & 15) - 8, 1.f / 16, gc, gs);
      x[e] = (row >> 4) == (ch >> 1) ? gc : (ch >> 1) ? gs : -gs;
    }
    v[i] = pack2(c[0] * 0.125f, c[1] * 0.125f);
    v[4 + i] = pack2(s[0] * 0.125f, s[1] * 0.125f);
    v[8 + i] = pack2(x[0], x[1]);
  }
#pragma unroll
  for (int i = 0; i < 12; i++) asm volatile("" : "+r"(v[i]));
}
__device__ __forceinline__ void fft_tables_store(const uint32_t (&v)[12], uint32_t sb, int tw) {
  const int row = tw >> 2;
  const uint32_t x = ((tw ^ (row >> 1)) & 3) << 4, a = sb + OFF_FT + (16 * (row >> 3) + (row & 7)) * 64 + x;
  sts128(a, v[0], v[1], v[2], v[3]);
  sts128(a + 512, v[4], v[5], v[6], v[7]);
  sts128(sb + OFF_GT + row * 64 + x, v[8], v[9], v[10], v[11]);
}
__device__ __forceinline__ void fft_twiddles(uint32_t (&v)[2], int tw) {
  float a[2], s[2];
#pragma unroll
  for (int i = 0; i < 2; i++) {
    float c;
    cis((2 * (2 * (tw & 3) + i) - 15) * (4 * (tw >> 2) - 63), 1.f / 4096, c, s[i]);
    a[i] = __fdividef(-s[i], 1.f + c);
  }
  v[0] = pack2(a[0], a[1]);
  v[1] = pack2(s[0], s[1]);
  asm volatile("" : "+r"(v[0]), "+r"(v[1]));
}
__device__ __forceinline__ void fft_matrices(FftConst& k, uint32_t sb, int w, int lane) {
  const uint32_t x = (lane >> 1) & 3;
  const uint2 t0 = lds64(sb + OFF_TT + 256 * w + 8 * lane), t1 = lds64(sb + OFF_TT + 256 * w + 8 * (lane ^ 3));
  k.ta[0][0] = t0.x;
  k.tb[0][0] = t0.y;
  k.ta[1][1] = __byte_perm(t1.x, 0, 0x1032);
  k.tb[1][1] = __byte_perm(t1.y, 0, 0x1032);
#pragma unroll
  for (int j = 0; j < 2; j++) {
    k.ta[1 - j][j] = k.ta[j][j] ^ 0x80008000u;
    k.tb[1 - j][j] = k.tb[j][j] ^ 0x80008000u;
    asm volatile("" : "+r"(k.ta[0][j]), "+r"(k.tb[0][j]), "+r"(k.ta[1][j]), "+r"(k.tb[1][j]));
  }
#pragma unroll
  for (int i = 0; i < 2; i++) {
    ldsm4(k.f[i], sb + OFF_FT + (16 * w + (lane & 15)) * 64 + (((2 * i + (lane >> 4)) ^ x) << 4));
    ldsm4t(k.fi[i], sb + OFF_FT + (32 * i + lane) * 64 + ((w ^ x) << 4));
#pragma unroll
    for (int j = 0; j < 4; j++) {
      k.fi[2 + i][j] = (j & 1) ? k.fi[i][j - 1] ^ 0x80008000u : k.fi[i][j + 1];
      asm volatile("" : "+r"(k.fi[2 + i][j]));
    }
  }
}
__device__ __forceinline__ void rot(uint32_t& x, uint32_t& y, uint32_t a, uint32_t b) {
  x = bfma(a, y, x);
  y = bfma(b, x, y);
  x = bfma(a, y, x);
}
__device__ __forceinline__ void twiddle_fwd(uint32_t (&a)[4][4], float* d, const FftConst& k) {
#pragma unroll
  for (int q = 0; q < 4; q++)
#pragma unroll
    for (int j = 0; j < 2; j++) {
      const float* x = d + 8 * q + 4 * j;
      uint32_t re = pack2(x[0], x[1]), im = pack2(x[2], x[3]);
      rot(re, im, k.ta[0][j], k.tb[0][j]);
      a[q & 2][2 * j + (q & 1)] = re;
      a[(q & 2) + 1][2 * j + (q & 1)] = im;
    }
}
__device__ __forceinline__ void g_step(float* d, const uint32_t (&a)[4][4], uint32_t dre, uint32_t dim) {
  WgRS<32>::set<HI_SW64>(d, a[0], dre);
  WgRS<32>::set<HI_SW64>(d + 16, a[2], dre);
  WgRS<32>::mma<HI_SW64>(d, a[1], dim);
  WgRS<32>::mma<HI_SW64>(d + 16, a[3], dim);
  wg_commit();
}

__device__ __forceinline__ void products(uint32_t (&a)[4][4], const float* H, const float* U, int p) {
#pragma unroll
  for (int j = 0; j < 2; j++)
#pragma unroll
    for (int m = 2 * p; m < 2 * p + 2; m++) {
      float pr[2], pi[2];
#pragma unroll
      for (int x = 0; x < 2; x++)
#pragma unroll
        for (int q = 0; q <= m; q++) {
          const int ih = 16 * (q >> 1) + 2 * (q & 1) + 4 * j + x, iu = 16 * ((m - q) >> 1) + 2 * ((m - q) & 1) + 4 * j + x;
          pr[x] = q ? fmaf(H[ih], U[iu], pr[x]) : H[ih] * U[iu];
          pi[x] = q ? fmaf(H[ih], U[iu + 8], pi[x]) : H[ih] * U[iu + 8];
          pr[x] = fmaf(-H[ih + 8], U[iu + 8], pr[x]);
          pi[x] = fmaf(H[ih + 8], U[iu], pi[x]);
        }
      a[m & 2][2 * j + (m & 1)] = pack2(pr[0], pr[1]);
      a[(m & 2) + 1][2 * j + (m & 1)] = pack2(pi[0], pi[1]);
    }
}

__device__ __forceinline__ void conv_channel(const FftConst& k, uint32_t sb, int c, int wg, int w, int lane) {
  const uint32_t cb = sb + off_ch(c), bars = sb + OFF_BAR;
  const uint32_t du = desc_lo(cb, 1024), dg = desc_lo(sb + OFF_GT, 16), dz = desc_lo(cb + U_BYTES, 16);
  float U[32], H[32];
  uint32_t a[4][4], e[4][4];
  const float dv = __uint_as_float(lds32(sb + OFF_D + 4 * c));
  wg_fence();
  WgRS<64>::set<HI_SW32>(H, k.f[0], du + 256);
  WgRS<64>::mma<HI_SW32>(H, k.f[1], du + 256 + 32);
  wg_commit();
  wg_wait<0>();
  pin<32>(H);
  twiddle_fwd(a, H, k);
  mbar_wait(bars + 8 * (B_U + (c < 3 ? c : 3)), 0);
  TSM(w == 0 && c < 3, 7 + wg);
  wg_fence();
  WgRS<64>::set<HI_SW32>(U, k.f[0], du);
  WgRS<64>::mma<HI_SW32>(U, k.f[1], du + 32);
  wg_commit();
  g_step(H, a, dg, dg + 64);
  wg_wait<1>();
  pin<32>(U);
  twiddle_fwd(e, U, k);
  wg_fence();
  g_step(U, e, dg, dg + 64);
  wg_wait<0>();
  pin<32>(U);
  pin<32>(H);
#pragma unroll
  for (int j = 0; j < 4; j++) H[4 * (j >> 1) + (j & 1)] += dv;
  float V[32];
#pragma unroll
  for (int p = 0; p < 2; p++) {
    products(a, H, U, p);
    wg_fence();
    WgRS<32>::set<HI_SW64>(V + 16 * p, a[2 * p], dg + 64);
    WgRS<32>::mma<HI_SW64>(V + 16 * p, a[2 * p + 1], dg);
    wg_commit();
  }
  const uint32_t za = cb + U_BYTES + (8 * w + (lane & 7)) * 128 + (((lane >> 3) ^ (lane & 7)) << 4);
  const uint32_t ya = cb + (lane >> 4) * 1024 + (8 * w + (lane & 7)) * 32 + ((((lane >> 3) ^ (lane >> 2)) & 1) << 4);
  wg_sync(1 + wg);
#pragma unroll
  for (int p = 0; p < 2; p++) {
    if (p == 0) wg_wait<1>();
    else wg_wait<0>();
    pin<16>(V + 16 * p);
#pragma unroll
    for (int i = 0; i < 4; i++) {
      const int j = i & 1;
      const float* x = V + 16 * p + 4 * j + (i & 2);
      e[p][i] = pack2(x[8], x[9]);
      e[2 + p][i] = pack2(x[0], x[1]);
      rot(e[p][i], e[2 + p][i], k.ta[1][j], k.tb[1][j]);
    }
    stsm4(za ^ (64 * p), e[p]);
    stsm4((za ^ (64 * p)) + 4096, e[2 + p]);
  }
  fence_async_smem();
  wg_sync(1 + wg);
  wg_fence();
  WgRS<64>::set<HI_SW128>(H, k.fi[0], dz);
#pragma unroll
  for (int ks = 1; ks < 4; ks++) WgRS<64>::mma<HI_SW128>(H, k.fi[ks], dz + 128 * ks);
  wg_commit();
  wg_wait<0>();
  pin<32>(H);
  if (lane == 0) mbar_arrive(bars + 8 * B_CVD);
  TSIF(w == 0, 88 + c);
#pragma unroll
  for (int j = 0; j < 8; j++)
    a[j >> 2][j & 3] = j < 2 ? pack2(H[4 * j], H[4 * j + 1]) : pack2(H[4 * j] + H[4 * j - 6], H[4 * j + 1] + H[4 * j - 5]);
  stsm4(ya, a[0]);
  stsm4(ya + 2048, a[1]);
  fence_async_smem();
  __syncwarp();
}

__device__ __forceinline__ void prep_slab(uint4* res, const uint2* sw, uint32_t sb, int slab, int w, int lane) {
  const int t = lane & 3, tp = (lane & 7) >> 1, pos = 8 * tp + 2 * (((lane >> 3) + tp) & 3) + (lane & 1);
  const uint32_t base = sb + OFF_KVS + slab * KVS_BYTES + pos * 128;
  uint32_t kk[2][4][4], vv[2][4];
  mbar_wait(sb + OFF_BAR + 8 * (B_KV + slab), 0);
#pragma unroll
  for (int h = 0; h < 2; h++) {
#pragma unroll
    for (int j = 0; j < 4; j++) {
      const uint32_t a = base + 128 * j;
      ldsm4t(kk[h][j], a + (((w + 4 * h) ^ ((a >> 7) & 7)) << 4));
    }
    const uint32_t a = base + KVS_V;
    ldsm4t(vv[h], a + (((w + 4 * h) ^ ((a >> 7) & 7)) << 4));
  }
#pragma unroll
  for (int h = 0; h < 2; h++) {
    uint32_t (&k)[4][4] = kk[h];
    uint32_t (&v)[4] = vv[h];
    const uint32_t w0 = __byte_perm(sw[h].x, 0, 0x1010), w1 = __byte_perm(sw[h].x, 0, 0x3232);
    const uint32_t w2 = __byte_perm(sw[h].y, 0, 0x1010), w3 = __byte_perm(sw[h].y, 0, 0x3232);
#pragma unroll
    for (int m = 0; m < 4; m++)
      v[m] = bmul(badd(badd(badd(bmul(k[0][m], w3), bmul(k[1][m], w2)), bmul(k[2][m], w1)), bmul(k[3][m], w0)), v[m]);
    uint32_t a[4];
#pragma unroll
    for (int m = 0; m < 4; m++) a[m] = (t & 1) ? v[(m + 3) & 3] : v[m];
    res[h] = (t & 2) ? make_uint4(a[2], a[3], a[0], a[1]) : make_uint4(a[0], a[1], a[2], a[3]);
  }
}

__device__ __forceinline__ void prep_gate(const Params& p, uint32_t sb, int b, int w, int lane) {
  uint2 gw[5], x[4][5];
#pragma unroll
  for (int j = 0; j < 5; j++) gw[j] = ldg64(reinterpret_cast<const uint2*>(p.gate_w) + lane + 32 * j);
#pragma unroll
  for (int i = 0; i < 4; i++)
#pragma unroll
    for (int j = 0; j < 5; j++)
      x[i][j] = ldg64(reinterpret_cast<const uint2*>(p.q) + (16 * b + 4 * w + i) * (DIM / 4) + lane + 32 * j);
  float s[4];
#pragma unroll
  for (int i = 0; i < 4; i++) {
    s[i] = 0.f;
#pragma unroll
    for (int j = 0; j < 5; j++) {
      const uint32_t m0 = bmul(x[i][j].x, gw[j].x), m1 = bmul(x[i][j].y, gw[j].y);
      s[i] += (bf_lo(m0) + bf_hi(m0)) + (bf_lo(m1) + bf_hi(m1));
    }
  }
  const bool h = lane & 16, q = lane & 8;
  const float a = (h ? s[2] : s[0]) + __shfl_xor_sync(0xffffffffu, h ? s[0] : s[2], 16);
  const float c = (h ? s[3] : s[1]) + __shfl_xor_sync(0xffffffffu, h ? s[1] : s[3], 16);
  float z = (q ? c : a) + __shfl_xor_sync(0xffffffffu, q ? a : c, 8);
#pragma unroll
  for (int o = 4; o > 0; o >>= 1) z += __shfl_xor_sync(0xffffffffu, z, o);
  z = bf_lo(pack2(z, 0.f));
  z = bf_lo(pack2(__fdividef(1.f, 1.f + __expf(-z)), 0.f));
  mbar_wait(sb + OFF_BAR + 8 * B_S3, 0);
  if ((lane & 7) == 0) asm volatile("st.shared.f32 [%0], %1;" ::"r"(sb + OFF_GATE + 64 * (b & 7) + 16 * w + (lane >> 1)), "f"(z) : "memory");
  fence_async_smem();
}

__device__ __forceinline__ uint32_t bmax(uint32_t a, uint32_t b) {
  uint32_t d;
  asm("max.bf16x2 %0, %1, %2;" : "=r"(d) : "r"(a), "r"(b));
  return d;
}
__device__ __forceinline__ void softmax_two(const float (&l)[2][2], uint32_t& p0, uint32_t& p1) {
  constexpr float kScale = 0.22360679774997896f, kLog2e = 1.4426950408889634f;
  const uint32_t r0 = pack2(l[0][0], l[1][0]), r1 = pack2(l[0][1], l[1][1]);
  const uint32_t x0 = pack2(bf_lo(r0) * kScale, bf_hi(r0) * kScale), x1 = pack2(bf_lo(r1) * kScale, bf_hi(r1) * kScale);
  uint32_t m = bmax(x0, x1);
  m = bmax(m, __shfl_xor_sync(0xffffffffu, m, 1));
  m = bmax(m, __shfl_xor_sync(0xffffffffu, m, 2));
  const float m0 = bf_lo(m) * kLog2e, m1 = bf_hi(m) * kLog2e;
  p0 = pack2(ex2(bf_lo(x0) * kLog2e - m0), ex2(bf_lo(x1) * kLog2e - m0));
  p1 = pack2(ex2(bf_hi(x0) * kLog2e - m1), ex2(bf_hi(x1) * kLog2e - m1));
}

__device__ __forceinline__ void halo_read(uint32_t (&kpv)[10], uint32_t (&vpv)[10], uint32_t (&tg)[7], const uint4* hp) {
#pragma unroll
  for (int j = 0; j < 7; j++) {
    uint32_t x0, x1, x2;
    asm volatile("ld.relaxed.gpu.global.v4.u32 {%0, %1, %2, %3}, [%4];"
                 : "=r"(x0), "=r"(x1), "=r"(x2), "=r"(tg[j]) : "l"(hp + 32 * j) : "memory");
    if (j < 4) kpv[3 * j] = x0; else vpv[3 * j - 10] = x0;
    if (j < 3) kpv[3 * j + 1] = x1; else vpv[3 * j - 9] = x1;
    if (j < 3) kpv[3 * j + 2] = x2; else if (j < 6) vpv[3 * j - 8] = x2;
  }
}

template <int ROT>
__device__ __forceinline__ void pack_qkv(const float* acc, uint32_t (&qlo)[10], uint32_t (&qhi)[10], uint32_t (&klo)[10],
                                         uint32_t (&khi)[10], uint32_t (&vlo)[10], uint32_t (&vhi)[10]) {
#pragma unroll
  for (int j = 0; j < 10; j++) {
    const int x = (j + ROT) % 10, tq = x < 8 ? x : 16 + x, tk = x < 8 ? 8 + x : 18 + x, tv = x < 8 ? 16 + x : 20 + x;
    khi[j] = pack2(acc[4 * tk + 2], acc[4 * tk + 3]);
    vhi[j] = movm(pack2(acc[4 * tv + 2], acc[4 * tv + 3]));
    qlo[j] = pack2(acc[4 * tq], acc[4 * tq + 1]);
    qhi[j] = pack2(acc[4 * tq + 2], acc[4 * tq + 3]);
    klo[j] = pack2(acc[4 * tk], acc[4 * tk + 1]);
    vlo[j] = pack2(acc[4 * tv], acc[4 * tv + 1]);
    asm volatile("" : "+r"(khi[j]), "+r"(qlo[j]), "+r"(qhi[j]), "+r"(klo[j]), "+r"(vlo[j]));
  }
}

template <int ROT> __device__ __forceinline__ void halo_send(const float* acc, uint4* ho, uint32_t tag) {
#pragma unroll
  for (int j = 0; j < 7; j++) {
    uint32_t x[3];
#pragma unroll
    for (int e = 0; e < 3; e++) {
      const int i = 3 * j + e, y = (i % 10 + ROT) % 10, tk = y < 8 ? 8 + y : 18 + y, tv = y < 8 ? 16 + y : 20 + y;
      x[e] = i < 10 ? pack2(acc[4 * tk + 2], acc[4 * tk + 3]) : i < 20 ? movm(pack2(acc[4 * tv + 2], acc[4 * tv + 3])) : 0u;
    }
    asm volatile("st.relaxed.gpu.global.v4.u32 [%0], {%1, %2, %3, %4};" ::"l"(ho + 32 * j), "r"(x[0]), "r"(x[1]), "r"(x[2]), "r"(tag) : "memory");
  }
}

__device__ __forceinline__ void attention(float* acc, uint32_t sb, int b, int par, int w, int lane, uint32_t tag) {
  const int g = lane >> 2, t = lane & 3;
  uint32_t klo[10], khi[10], vlo[10], vhi[10], qlo[10], qhi[10], kpv[10], vpv[10];
  if (w == 3 && b < NCTA - 8) {
    uint4* ho = g_halo + (b * 2 + par) * 224 + lane;
    if (tail_first(b & 7)) halo_send<8>(acc, ho, tag);
    else halo_send<0>(acc, ho, tag);
    TSIF(par == 0, 76);
    pin<120>(acc);
  }
  if (tail_first(b & 7)) pack_qkv<8>(acc, qlo, qhi, klo, khi, vlo, vhi);
  else pack_qkv<0>(acc, qlo, qhi, klo, khi, vlo, vhi);
  const uint32_t xa = sb + OFF_KVX + (par * 3) * 2560 + lane * 16;
  if (w < 3) {
    sts128(xa + w * 2560, khi[0], khi[1], khi[2], khi[3]);
    sts128(xa + w * 2560 + 512, khi[4], khi[5], khi[6], khi[7]);
    sts128(xa + w * 2560 + 1024, khi[8], khi[9], vhi[0], vhi[1]);
    sts128(xa + w * 2560 + 1536, vhi[2], vhi[3], vhi[4], vhi[5]);
    sts128(xa + w * 2560 + 2048, vhi[6], vhi[7], vhi[8], vhi[9]);
  }
  TSIF(par == 0 && w == 1, 64);
#pragma unroll
  for (int j = 0; j < 10; j++) vlo[j] = movm(vlo[j]);
  const bool far0 = 2 * t > g, far1 = 2 * t + 1 > g;
  const uint32_t mfar = (far0 ? 0x0000FFFFu : 0u) | (far1 ? 0xFFFF0000u : 0u);
  float slo[4][2], lg[2][2];
  uint32_t phi[4], plo[4], qml[4], qmh[4];
#pragma unroll
  for (int h = 0; h < 4; h++) {
    const int f = h == 0 ? 0 : h == 1 ? 3 : h == 2 ? 5 : 8, hf = h < 2 ? 2 : 7;
    const bool mine = (h & 1) ? t >= 2 : t < 2;
    qml[h] = mine ? qlo[hf] : 0u;
    qmh[h] = mine ? qhi[hf] : 0u;
    float a[4] = {0.f, 0.f, 0.f, 0.f}, c[4] = {0.f, 0.f, 0.f, 0.f};
    mma16816(a, qlo[f], qhi[f], qlo[f + 1], qhi[f + 1], klo[f], klo[f + 1]);
    mma16816(c, qlo[f], qhi[f], qlo[f + 1], qhi[f + 1], khi[f], khi[f + 1]);
    mma1688(a, qml[h], qmh[h], klo[hf]);
    mma1688(c, qml[h], qmh[h], khi[hf]);
    slo[h][0] = a[0];
    slo[h][1] = a[1];
    lg[h & 1][0] = far0 ? a[2] : c[2];
    lg[h & 1][1] = far1 ? a[3] : c[3];
    if (h & 1) softmax_two(lg, phi[h - 1], phi[h]);
  }
  TSIF(par == 0 && w == 1, 65);
  wg_sync(1 + par);
  TSIF(par == 0 && w == 1, 66);
  const bool nohist = (w == 0) && (b < 8);
  const uint4* hp = g_halo + ((b - 8) * 2 + par) * 224 + lane;
  uint32_t tg[7];
  if (w > 0) {
    const uint4 v0 = lds128(xa + (w - 1) * 2560), v1 = lds128(xa + (w - 1) * 2560 + 512), v2 = lds128(xa + (w - 1) * 2560 + 1024);
    const uint4 v3 = lds128(xa + (w - 1) * 2560 + 1536), v4 = lds128(xa + (w - 1) * 2560 + 2048);
    kpv[0] = v0.x; kpv[1] = v0.y; kpv[2] = v0.z; kpv[3] = v0.w; kpv[4] = v1.x; kpv[5] = v1.y; kpv[6] = v1.z; kpv[7] = v1.w;
    kpv[8] = v2.x; kpv[9] = v2.y; vpv[0] = v2.z; vpv[1] = v2.w; vpv[2] = v3.x; vpv[3] = v3.y; vpv[4] = v3.z; vpv[5] = v3.w;
    vpv[6] = v4.x; vpv[7] = v4.y; vpv[8] = v4.z; vpv[9] = v4.w;
  } else if (nohist) {
#pragma unroll
    for (int j = 0; j < 10; j++) kpv[j] = vpv[j] = 0u;
  } else {
    TSIF(par == 0, 77);
    halo_read(kpv, vpv, tg, hp);
  }
  if (w == 0 && !nohist) {
    int spins = 0;
    while (true) {
      bool ok = true;
#pragma unroll
      for (int j = 0; j < 7; j++) ok = ok && tg[j] == tag;
      if (__all_sync(0xffffffffu, ok) || ++spins > SPIN_LIMIT) break;
      halo_read(kpv, vpv, tg, hp);
    }
    TSIF(par == 0, 79);
  }
#pragma unroll
  for (int h = 0; h < 4; h++) {
    const int f = h == 0 ? 0 : h == 1 ? 3 : h == 2 ? 5 : 8, hf = h < 2 ? 2 : 7;
    float a[4] = {0.f, 0.f, 0.f, 0.f};
    mma16816(a, qlo[f], qhi[f], qlo[f + 1], qhi[f + 1], kpv[f], kpv[f + 1]);
    mma1688(a, qml[h], qmh[h], kpv[hf]);
    const float ninf = __int_as_float(0xff800000);
    lg[h & 1][0] = far0 ? (nohist ? ninf : a[0]) : slo[h][0];
    lg[h & 1][1] = far1 ? (nohist ? ninf : a[1]) : slo[h][1];
    if (h & 1) softmax_two(lg, plo[h - 1], plo[h]);
  }
  TSIF(par == 0 && w <= 1, 67 + w);
  uint32_t ov[20];
#pragma unroll
  for (int hp = 0; hp < 2; hp++) {
    const int hf = hp ? 7 : 2;
    float sh[4] = {0.f, 0.f, 0.f, 0.f}, i0 = 0.f, i1 = 0.f;
#pragma unroll
    for (int e = 0; e < 2; e++) {
      const int h = 2 * hp + e, f = h == 0 ? 0 : h == 1 ? 3 : h == 2 ? 5 : 8;
      const uint32_t a0 = plo[h] & mfar, a2 = plo[h] & ~mfar, a3 = phi[h] & mfar, c1 = phi[h] & ~mfar;
      float sum[4] = {0.f, 0.f, 0.f, 0.f};
      mma1688(sum, plo[h], phi[h], 0x3F803F80u);
      const float r0 = rcp(sum[0]), r1 = rcp(sum[2]);
#pragma unroll
      for (int j = f; j < f + 2; j++) {
        float o[4] = {0.f, 0.f, 0.f, 0.f};
        mma16816(o, a0, 0u, a2, a3, vpv[j], vlo[j]);
        mma1688(o, 0u, c1, vhi[j]);
        ov[2 * j] = pack2(o[0] * r0, o[1] * r0);
        ov[2 * j + 1] = pack2(o[2] * r1, o[3] * r1);
      }
      const bool mine = e ? g >= 4 : g < 4;
      mma16816(sh, a0, 0u, a2, a3, mine ? vpv[hf] : 0u, mine ? vlo[hf] : 0u);
      mma1688(sh, 0u, c1, mine ? vhi[hf] : 0u);
      if (e == 0 || t >= 2) {
        i0 = r0;
        i1 = r1;
      }
    }
    ov[2 * hf] = pack2(sh[0] * i0, sh[1] * i0);
    ov[2 * hf + 1] = pack2(sh[2] * i1, sh[3] * i1);
  }
  TS(32 + 4 * par + w);
  mbar_wait(sb + OFF_BAR + 8 * B_P1, 0);
  const uint32_t oa = sb + OFF_OA + (lane >> 4) * 2048 + (32 * w + 2 * (lane & 15) + par) * 16;
#pragma unroll
  for (int j = 0; j < 5; j++) stsm4(oa + 4096 * j, ov + 4 * j);
  TSIF(par == 0 && w == 0, 120);
  fence_async_smem();
  TSIF(par == 0 && w == 0, 121);
  __syncwarp();
  if (lane == 0) mbar_arrive(sb + OFF_BAR + 8 * B_ATTN);
  TSM(w == 0 || w == 2, 122 + par + (w == 2 ? 3 : 0));
}

struct Maps {
  CUtensorMap x, wm, wt, k, v, y, wo, qm, qt, om, ot, yl, ol;
};

__device__ __forceinline__ void load_stage(uint32_t sb, int kb, int b, const Maps& m) {
  const uint32_t st = sb + (kb & 3) * STAGE_BYTES, bar = sb + OFF_BAR + 8 * (B_FULL1 + (kb & 3));
  const int r = b >> 3, hg = b & 7, slab = kb - KV_KB;
  const bool kv = slab >= 0 && slab < 5;
  const uint32_t kbar = sb + OFF_BAR + 8 * (B_KV + slab), dst = sb + OFF_KVS + slab * KVS_BYTES;
  mbar_expect_tx(bar, STAGE_BYTES);
  if (kv) mbar_expect_tx(kbar, KVS_BYTES);
  tma_3d(st, &m.x, 64 * kb, 64 * r, 0, bar);
  tma_3d(st + ST_W, &m.wm, 80 * hg + (tail_first(hg) ? 16 : 0), 64 * kb, 0, bar);
  tma_3d(st + ST_WT, &m.wt, 80 * hg + (tail_first(hg) ? 0 : 64), 64 * kb, 0, bar);
  if (kv) tma_3d(dst, &m.k, 0, 32 * (b >> 1) - 3, 2 * slab + (b & 1), kbar);
  if (kv) tma_3d(dst + KVS_V, &m.v, 0, 32 * (b >> 1), 2 * slab + (b & 1), kbar);
}

__global__ void __launch_bounds__(NTHR, 1) fused_kernel(const __grid_constant__ Maps m, const Params p) {
  extern __shared__ __align__(1024) uint8_t smem[];
  const uint32_t sb = (uint32_t)__cvta_generic_to_shared(smem);
  const uint32_t bars = sb + OFF_BAR;
  const int tid = threadIdx.x, lane = tid & 31;
  int b = blockIdx.x;
  b = (((b & 63) >> 3) * 2 + (b & 1)) * 8 + (((b < 64 ? 0x6521 : 0x7430) >> (4 * ((b >> 1) & 3))) & 7);
  const int r = b >> 3, hg = b & 7;

  if (tid == T_ISSUE) {
    TSM(true, 0);
    mbar_init(bars + 8 * B_F0, 1);
    fence_async_smem();
    mbar_expect_tx(bars + 8 * B_F0, ST_WT);
    tma_3d(sb, &m.x, 0, 64 * r, 0, bars + 8 * B_F0);
    tma_3d(sb + ST_W, &m.wm, 80 * hg + (tail_first(hg) ? 16 : 0), 0, 0, bars + 8 * B_F0);
#pragma unroll
    for (int i = 0; i < 4; i++) mbar_init(bars + 8 * (B_FULL1 + i), 1);
    fence_async_smem();
    mbar_expect_tx(bars + 8 * B_FULL1, STAGE_BYTES - ST_WT);
    tma_3d(sb + ST_WT, &m.wt, 80 * hg + (tail_first(hg) ? 0 : 64), 0, 0, bars + 8 * B_FULL1);
    load_stage(sb, 1, b, m);
  } else if (tid == T_INIT) {
#pragma unroll
    for (int i = 0; i < B_F0; i++) mbar_init(bars + 8 * i, i < B_GATE ? 8 : i < B_CVD ? 4 : i == B_CVD ? 20 : 1);
    fence_async_smem();
  }
  const int warp = __shfl_sync(0xffffffffu, tid >> 5, 0), wg = warp >> 2, w = warp & 3;
  __syncthreads();

  if (wg == 3) {
    asm volatile("setmaxnreg.dec.sync.aligned.u32 56;");
    if (w == 0) {
      if (lane == 0) {
#pragma unroll 1
        for (int kb = 2; kb < 10; kb++) {
          if (kb >= 4) mbar_wait(bars + 8 * (kb == 7 ? B_E3 : B_EMPTY1 + (kb & 3)), (kb >> 3) & 1);
          TSIF(kb >= 4, 44 + kb);
          load_stage(sb, kb, b, m);
          TSIF(kb == 3, 60);
          if (kb == TRIG_KB) mbar_arrive(bars + 8 * B_LAST);
        }
        mbar_wait(bars + 8 * B_WOP, 0);
        mbar_wait(bars + 8 * WL_TRIG, 0);
        mbar_wait(bars + 8 * B_EPOCH, 0);
        flag_wait(g_cnt + C_W + 32 * hg, (lds32(sb + OFF_EPOCH) + 1) * 16);
        TS(30);
#pragma unroll 1
        for (int j = 0; j < 8; j++) {
          if (j >= 6) mbar_wait(bars + 8 * (B_EMPTY2 + j - 6), 0);
          if (j == 4) mbar_wait(bars + 8 * (RB32 & 2 ? B_ORB : B_ATTN), 0);
          TSIF(j >= 6, 100 + j);
          mbar_expect_tx(bars + 8 * (B_FULL2 + j), j == 0 ? WO_BYTES : j == 5 ? O_BYTES + WO_BYTES + 512 : O_BYTES + WO_BYTES);
          bulk_load(sb + off_w(j), g_WO + (hg * 8 + step_src(hg, j)) * 800, WO_BYTES, bars + 8 * (B_FULL2 + j));
        }
        mbar_wait(bars + 8 * (B_EMPTY2 + 3), 0);
        mbar_expect_tx(bars + 8 * B_QF, O_BYTES);
        tma_2d(sb + OFF_QS, &m.qm, 80 * hg, 128 * r, bars + 8 * B_QF);
        tma_2d(sb + OFF_QT, &m.qt, 80 * hg + 64, 128 * r, bars + 8 * B_QF);
      }
    } else if (w == 1) {
      unsigned epoch = 0;
      if (lane == 0) {
        epoch = atomicAdd(g_cnt + C_LAUNCH, 1u) / NCTA;
        asm volatile("st.shared.u32 [%0], %1;" ::"r"(sb + OFF_EPOCH), "r"(epoch) : "memory");
        mbar_arrive(bars + 8 * B_EPOCH);
        mbar_wait(bars + 8 * B_KVD, 0);
        mbar_expect_tx(bars + 8 * B_HB, 5 * 4096);
#pragma unroll 1
        for (int c = 0; c < 5; c++) {
          if (c == 3) mbar_wait(bars + 8 * B_S3, 0);
          bulk_load(sb + off_ch(c) + U_BYTES, p.ssm_k + (5 * b + c) * SEQ, 4096, bars + 8 * B_HB);
        }
#pragma unroll
        for (int c = 0; c < 4; c++) mbar_expect_tx(bars + 8 * (B_U + c), c < 3 ? U_BYTES : 2 * U_BYTES);
        const uint4* usrc = g_U + 5 * b * U_PITCH;
        mbar_wait(bars + 8 * B_USIG, 0);
        flag_wait(g_cnt + C_PREP + 32 * (b & 15), (epoch + 1) * NCTA);
        TS(23);
#pragma unroll
        for (int c = 0; c < 5; c++) {
          if (c == 3) mbar_wait(bars + 8 * (B_U + 2), 0);
          bulk_load(sb + off_ch(c), usrc + c * U_PITCH, U_BYTES, bars + 8 * (B_U + (c < 3 ? c : 3)));
          TSIF(c == 0 || c == 4, 116 + (c >> 2));
        }
      }
      epoch = __shfl_sync(0xffffffffu, epoch, 0);
      if (lane < 8) {
        const int src = (b & ~7) | step_src(hg, lane);
        mbar_wait(bars + 8 * B_ATTN, 0);
        TS(20);
        bool seen = false;
#pragma unroll 1
        for (int spins = 0; spins < SPIN_LIMIT; spins++) {
          const bool now = !seen && (int)(flag_read(g_cnt + C_O + 32 * src) - (epoch + 1)) >= 0;
          if (now && lane >= 1 && lane < 4) bulk_load(sb + off_o(lane), g_O + src * 1280, O_BYTES, bars + 8 * (B_FULL2 + lane));
          seen = seen || now;
          if (__all_sync(0xff, seen)) break;
        }
        TS(21);
        if (lane == 5) bulk_load(sb + OFF_GATE, g_gate + 128 * r, 512, bars + 8 * (B_FULL2 + 5));
#pragma unroll 1
        for (int j = 4; j < 8; j++) {
          if (lane == j) {
            mbar_wait(bars + 8 * (j < 6 ? B_C34 : B_EMPTY2 + j - 6), 0);
            bulk_load(sb + off_o(j), g_O + src * 1280, O_BYTES, bars + 8 * (B_FULL2 + j));
          }
          __syncwarp(0xff);
        }
        TS(22);
      }
    } else if (w == 2) {
      mbar_wait(bars + 8 * B_PREP, 0);
      flag_signal(g_cnt + C_PREP, 16, lane);
      TS(25);
      if (lane == 0) {
        mbar_arrive(bars + 8 * B_USIG);
        mbar_expect_tx(bars + 8 * B_ORB, (RB32 & 2 ? O_BYTES / 4 : O_BYTES) + 64);
        mbar_wait(bars + 8 * B_GATE, 0);
        publish(g_gate + 16 * b, sb + OFF_GATE + 64 * hg, 64, bars + 8 * B_ORB);
        mbar_wait(bars + 8 * B_ATTN, 0);
        if (RB32 & 2) {
          bulk_store(g_O + b * 1280, sb + OFF_OA, O_BYTES);
          bulk_wait_read();
          tma_2d(sb + OFF_KVX + 10240, &m.ol, 48, b * 160, bars + 8 * B_ORB);
        } else {
          publish(g_O + b * 1280, sb + OFF_OA, O_BYTES, bars + 8 * B_ORB);
        }
        TS(74);
        mbar_wait(bars + 8 * B_ORB, 0);
        flag_bump(g_cnt + C_O + 32 * b);
        TS(26);
        mbar_arrive(bars + 8 * B_OSIG);
      }
    } else {
      if (lane == 0) {
        uint4* dst = g_WO + (hg * 8 + (r >> 1)) * 800 + (r & 1) * 80;
        mbar_wait(bars + 8 * B_S3, 0);
        asm volatile("cp.async.bulk.prefetch.L2.global [%0], 6400;" ::"l"(p.wo + b * 3200) : "memory");
        mbar_wait(bars + 8 * B_P1, 0);
        mbar_wait(bars + 8 * WB_TRIG, 0);
        mbar_expect_tx(bars + 8 * B_WST, WO_BYTES / 2);
        tma_3d(sb + OFF_WA, &m.wo, 0, 40 * r, 5 * hg, bars + 8 * B_WST);
        mbar_wait(bars + 8 * B_WST, 0);
#pragma unroll 1
        for (int n = 0; n < 5; n++) bulk_store(dst + 160 * n, sb + OFF_WA + 1280 * n, 1280);
        bulk_wait_read();
        mbar_expect_tx(bars + 8 * B_WST, WO_BYTES / 2);
#pragma unroll 1
        for (int n = 0; n < 5; n++) bulk_load(sb + OFF_WA + 1280 * n, dst + 160 * n, 1280, bars + 8 * B_WST);
        mbar_wait(bars + 8 * B_WST, 1);
        flag_bump(g_cnt + C_W + 32 * hg);
        mbar_arrive(bars + 8 * B_WOP);
        TS(71);
        mbar_expect_tx(bars + 8 * B_C34, 3 * (RB32 & 1 ? 1024 : U_BYTES));
        mbar_expect_tx(bars + 8 * B_YRB, 2 * (RB32 & 1 ? 1024 : U_BYTES));
#pragma unroll 1
        for (int c = 0; c < 5; c++) {
          mbar_wait(bars + 8 * (B_YST + c), 0);
          if (RB32 & 1) {
            bulk_store(g_U + (5 * b + c) * U_PITCH, sb + off_ch(c), U_BYTES);
            bulk_wait_read();
            tma_2d(sb + off_ch(c), &m.yl, 48, (5 * b + c) * (U_PITCH / 8), bars + 8 * (c < 3 ? B_C34 : B_YRB));
          } else {
            publish(g_U + (5 * b + c) * U_PITCH, sb + off_ch(c), U_BYTES, bars + 8 * (c < 3 ? B_C34 : B_YRB));
          }
        }
        TS(75);
        mbar_wait(bars + 8 * B_C34, 0);
        mbar_wait(bars + 8 * B_YRB, 0);
        flag_bump(g_cnt + C_Y + 32 * (b >> 4));
        TS(27);
        mbar_arrive(bars + 8 * B_YSIG);
        mbar_expect_tx(bars + 8 * B_YFULL, 20480);
        flag_wait(g_cnt + C_Y + 32 * hg, (lds32(sb + OFF_EPOCH) + 1) * 16);
        TS(24);
        tma_2d(sb + OFF_YT, &m.y, 128 * r, 80 * hg, bars + 8 * B_YFULL);
        tma_2d(sb + OFF_YT + 10240, &m.y, 128 * r + 64, 80 * hg, bars + 8 * B_YFULL);
      }
    }
  } else {
    asm volatile("setmaxnreg.inc.sync.aligned.u32 152;");
    if (wg < 2) {
      float acc[120];
#pragma unroll
      for (int i = 0; i < 120; i++) acc[i] = 0.f;
      const uint32_t da = desc_lo(sb + wg * 8192, 16), db = desc_lo(sb + ST_W, 8192), dc = desc_lo(sb + ST_WT, 2048);
      mbar_wait(bars + 8 * B_F0, 0);
      TSIF(w == 0 && wg == 0, 1);
      wg_fence();
#pragma unroll
      for (int k = 0; k < 4; k++) WgSST<192>::mma<HI_SW128, HI_SW128>(acc, da + 2 * k, db + 128 * k, 1);
      wg_commit();
      mbar_wait(bars + 8 * B_FULL1, 0);
      wg_fence();
#pragma unroll
      for (int k = 0; k < 4; k++) WgSST<48>::mma<HI_SW128, HI_SW32>(acc + 96, da + 2 * k, dc + 32 * k, 1);
      wg_commit();
#pragma unroll 1
      for (int kb = 1; kb < 10; kb++) {
        mbar_wait(bars + 8 * (B_FULL1 + (kb & 3)), (kb >> 2) & 1);
        const uint32_t so = (kb & 3) * (STAGE_BYTES >> 4);
        wg_fence();
#pragma unroll
        for (int k = 0; k < 4; k++) {
          WgSST<192>::mma<HI_SW128, HI_SW128>(acc, da + so + 2 * k, db + so + 128 * k, 1);
          WgSST<48>::mma<HI_SW128, HI_SW32>(acc + 96, da + so + 2 * k, dc + so + 32 * k, 1);
        }
        wg_commit();
        wg_wait<1>();
        if (lane == 0) mbar_arrive(bars + 8 * (kb == 4 ? B_E3 : B_EMPTY1 + ((kb - 1) & 3)));
      }
      mbar_wait(bars + 8 * B_EPOCH, 0);
      const uint32_t tag = lds32(sb + OFF_EPOCH) + 1;
      mbar_wait(bars + 8 * B_S3, 0);
      wg_wait<0>();
      pin<120>(acc);
      if (lane == 0) mbar_arrive(bars + 8 * B_P1);
      TSM(w == 0, 3 + wg);
      attention(acc, sb, b, wg, w, lane, tag);
    } else {
      const int tw = tid & 127, chl = 64 * (b & 1) + 8 * w + (lane >> 2);
      uint4* up = g_U + chl * U_PITCH + ((4 * (b >> 1) + (lane & 3)) ^ ((b >> 2) & 1));
      uint2 sw[10];
      uint32_t dv = 0;
      if (lane < 5) dv = __ldg(reinterpret_cast<const unsigned short*>(p.ssm_D) + 5 * b + lane);
#pragma unroll
      for (int i = 0; i < 10; i++) sw[i] = ldg64(reinterpret_cast<const uint2*>(p.shift_k) + chl + 128 * (i >> 1) + 32 * (i & 1));
      uint32_t tab[12];
      uint32_t tt[2];
      fft_tables(tab, tw);
      fft_twiddles(tt, tw);
      uint4 res[10];
#pragma unroll
      for (int i = 0; i < 10; i++) res[i] = make_uint4(0, 0, 0, 0);
#pragma unroll 1
      for (int slab = 0; slab < 5; slab++) {
#pragma unroll
        for (int i = 0; i < 8; i++) res[i] = res[i + 2];
        prep_slab(res + 8, sw, sb, slab, w, lane);
        TSIF(w == 0, 99 + 4 * slab);
#pragma unroll
        for (int i = 0; i < 8; i++) sw[i] = sw[i + 2];
      }
      TSIF(w == 0, 28);
      __syncwarp();
      if (lane == 0) mbar_arrive(bars + 8 * B_KVD + ((res[8].x ^ res[9].x) & p.zero));
      mbar_wait(bars + 8 * B_KVD, 0);
      fft_tables_store(tab, sb, tw);
      mbar_wait(bars + 8 * B_LAST, 0);
#pragma unroll
      for (int i = 0; i < 10; i++) up[(128 * (i >> 1) + 32 * (i & 1)) * U_PITCH] = res[i];
      __syncwarp();
      if (lane == 0) mbar_arrive(bars + 8 * B_PREP);
      TSIF(w == 0, 5);
      mbar_wait(bars + 8 * B_LAST, 0);
      prep_gate(p, sb, b, w, lane);
      __syncwarp();
      if (lane == 0) mbar_arrive(bars + 8 * B_GATE);
      TSIF(w == 0, 72);
      mbar_wait(bars + 8 * B_HB, 0);
      TSIF(w == 0, 2);
      const uint32_t ha = sb + U_BYTES + ((tw >> 3) * 16 + 8 + (tw & 7)) * 16;
      uint4 hv[5];
#pragma unroll
      for (int c = 0; c < 5; c++) hv[c] = lds128(ha + off_ch(c));
      __syncwarp();
#pragma unroll
      for (int c = 0; c < 5; c++) sts128((ha ^ 16) + off_ch(c), hv[c].x, hv[c].y, hv[c].z, hv[c].w);
      asm volatile("st.shared.v2.u32 [%0], {%1, %2};" ::"r"(sb + OFF_TT + 8 * tw), "r"(tt[0]), "r"(tt[1]) : "memory");
      if (tw < 5) asm volatile("st.shared.f32 [%0], %1;" ::"r"(sb + OFF_D + 4 * tw), "f"(bf_lo(dv) * 0.125f) : "memory");
      fence_async_smem();
      __syncwarp();
      if (lane == 0) mbar_arrive(bars + 8 * B_HA);
      TSIF(w == 0, 6);
    }

    FftConst fc;
    TSM(w == 0 && wg == 0, 104);
    mbar_wait(bars + 8 * B_HA, 0);
    fft_matrices(fc, sb, w, lane);
    TSM(w == 0 && wg == 0, 105);
    TSM(w == 0 && wg == 2, 124);
#pragma unroll 1
    for (uint32_t tasks = wg == 0 ? TASK0 : wg == 1 ? TASK1 : TASK2; tasks; tasks >>= 4) {
      const int c = (tasks & 7) - 1;
      conv_channel(fc, sb, c, wg, w, lane);
      if (lane == 0) mbar_arrive(bars + 8 * (B_YST + c));
      TSM(w == 0, 10 + c);
    }

    if (wg != WO_SKIP) {
      const int wg = (warp >> 2) > WO_SKIP ? (warp >> 2) - 1 : warp >> 2;
      const int g = lane >> 2;
      float acc[40];
#pragma unroll
      for (int i = 0; i < 40; i++) acc[i] = 0.f;
      const uint32_t da = desc_lo(sb + wg * 1024, 2048), db = desc_lo(sb, 2560);
      mbar_wait(bars + 8 * B_ORB, 0);
      mbar_wait(bars + 8 * B_FULL2, 0);
      mbar_wait(bars + 8 * B_CVD, 0);
      TSM(w == 0, 15 + wg);
#pragma unroll 1
      for (int j = 0; j < 8; j++) {
        mbar_wait(bars + 8 * (B_FULL2 + j), 0);
        TSM(w == 0 && wg == 0, 44 + (j < 4 ? j : j + 6));
        const uint32_t oa = da + (off_o(j) >> 4), ob = db + (off_w(j) >> 4);
        wg_fence();
#pragma unroll
        for (int k = 0; k < 5; k++) WgSST<80>::mma<HI_NONE, HI_SW32>(acc, oa + 256 * k, ob + 32 * k, 1);
        wg_commit();
        wg_wait<1>();
        if (j >= 1 && j <= 4 && lane == 0) mbar_arrive(bars + 8 * (B_EMPTY2 + j - 1));
      }
      TSIF(w == 0 && wg == 0, 113);
      const int tr = 64 * wg + 16 * w + (lane & 15);
      const uint32_t fm = sb + OFF_QS + tr * 128, fx = (lane >> 4) ^ (tr & 7);
      const uint32_t ft = sb + OFF_QT + tr * 32 + (((lane >> 4) ^ (tr >> 2)) & 1) * 16;
      const float g0 = __uint_as_float(lds32(sb + OFF_GATE + (64 * wg + 16 * w + g) * 4));
      const float g1 = __uint_as_float(lds32(sb + OFF_GATE + (64 * wg + 16 * w + 8 + g) * 4));
      const uint32_t ga = pack2(g0, g0), gb = pack2(g1, g1);
      const uint32_t na = pack2(1.f - g0, 1.f - g0), nb = pack2(1.f - g1, 1.f - g1);

      const uint32_t ya = sb + OFF_YT + wg * 10240 + ((lane >> 4) * 8 + (lane & 7)) * 128 +
                          (((2 * w + (((lane >> 3) & 1) ^ wg)) ^ (lane & 7)) << 4);
      uint32_t qf[20], y[20];
      mbar_wait(bars + 8 * B_QF, 0);
      TSM(w == 0 && wg == 0, 99);
#pragma unroll
      for (int j = 0; j < 5; j++) ldsm4(qf + 4 * j, j < 4 ? fm + ((fx ^ (2 * j)) << 4) : ft);
      mbar_wait(bars + 8 * B_YFULL, 0);
      TSM(w == 0 && wg == 0, 19);
#pragma unroll
      for (int j = 0; j < 5; j++) ldsm4t(y + 4 * j, ya + 2048 * j);
#pragma unroll
      for (int i = 0; i < 20; i++) {
        qf[i] = bmul((i & 1) ? gb : ga, bmul(qf[i], y[i]));
        asm volatile("" : "+r"(qf[i]));
      }
      wg_wait<0>();
      pin<40>(acc);
      TSM(w == 0, 17 + wg);
#pragma unroll
      for (int i = 0; i < 20; i++) qf[i] = bfma((i & 1) ? nb : na, pack2(acc[2 * i], acc[2 * i + 1]), qf[i]);
#pragma unroll
      for (int j = 0; j < 5; j++) stsm4(j < 4 ? fm + ((fx ^ (2 * j)) << 4) : ft, qf + 4 * j);
      fence_async_smem();
      __syncwarp();
      if (lane == 0) {
        const int row = 64 * wg + 16 * w;
        asm volatile("cp.async.bulk.tensor.2d.global.shared::cta.bulk_group [%0, {%2, %3}], [%1];"
                     ::"l"(&m.om), "r"(sb + OFF_QS + row * 128), "r"(80 * hg), "r"(128 * r + row) : "memory");
        asm volatile("cp.async.bulk.tensor.2d.global.shared::cta.bulk_group [%0, {%2, %3}], [%1];"
                     ::"l"(&m.ot), "r"(sb + OFF_QT + row * 32), "r"(80 * hg + 64), "r"(128 * r + row) : "memory");
        asm volatile("cp.async.bulk.commit_group;\ncp.async.bulk.wait_group.read 0;" ::: "memory");
      }
      TSM(w == 0 || w == 3, 40 + 2 * wg + (w & 1));
    }
  }
}

typedef CUresult (*EncodeFn)(CUtensorMap*, CUtensorMapDataType, cuuint32_t, void*, const cuuint64_t*, const cuuint64_t*,
                             const cuuint32_t*, const cuuint32_t*, CUtensorMapInterleave, CUtensorMapSwizzle,
                             CUtensorMapL2promotion, CUtensorMapFloatOOBfill);

void encode(EncodeFn fn, CUtensorMap* tm, const void* base, int rank, const cuuint64_t* dims, const cuuint64_t* strides,
            const cuuint32_t* box, CUtensorMapSwizzle swz) {
  const cuuint32_t ones[3] = {1, 1, 1};
  fn(tm, CU_TENSOR_MAP_DATA_TYPE_BFLOAT16, rank, const_cast<void*>(base), dims, strides, box, ones,
     CU_TENSOR_MAP_INTERLEAVE_NONE, swz, CU_TENSOR_MAP_L2_PROMOTION_L2_128B, CU_TENSOR_MAP_FLOAT_OOB_FILL_NONE);
}

}

extern "C" void kernel_launch(void* const* d_in, const int* in_sizes, int n_in, void* d_out, int out_size) {
  (void)in_sizes; (void)n_in; (void)out_size;
  Params p;
  p.q = (const __nv_bfloat16*)d_in[0];
  p.k = (const __nv_bfloat16*)d_in[1];
  p.v = (const __nv_bfloat16*)d_in[2];
  p.shift_k = (const __nv_bfloat16*)d_in[3];
  p.ssm_k = (const __nv_bfloat16*)d_in[4];
  p.ssm_D = (const __nv_bfloat16*)d_in[5];
  p.wqkv = (const __nv_bfloat16*)d_in[7];
  p.wo = (const __nv_bfloat16*)d_in[8];
  p.gate_w = (const __nv_bfloat16*)d_in[9];
  p.out = (__nv_bfloat16*)d_out;
  p.zero = 0;

  static EncodeFn fn = nullptr;
  static void *yaddr = nullptr, *oaddr = nullptr;
  if (!fn) {
    cudaDriverEntryPointQueryResult qr;
    void* f = nullptr;
    cudaGetDriverEntryPoint("cuTensorMapEncodeTiled", &f, cudaEnableDefault, &qr);
    fn = (EncodeFn)f;
    cudaGetSymbolAddress(&yaddr, g_U);
    cudaGetSymbolAddress(&oaddr, g_O);
    cudaFuncSetAttribute(fused_kernel, cudaFuncAttributeMaxDynamicSharedMemorySize, SMEM_BYTES);
  }
  Maps m;
  {
    const cuuint64_t dims[3] = {640, 1024, 2}, st[2] = {2560, 1280};
    const cuuint32_t box[3] = {64, 64, 2};
    encode(fn, &m.x, p.q, 3, dims, st, box, CU_TENSOR_MAP_SWIZZLE_128B);
  }
  {
    const cuuint64_t dims[3] = {640, 640, 3}, st[2] = {3840, 1280};
    const cuuint32_t box[3] = {64, 64, 3}, boxt[3] = {16, 64, 3};
    encode(fn, &m.wm, p.wqkv, 3, dims, st, box, CU_TENSOR_MAP_SWIZZLE_128B);
    encode(fn, &m.wt, p.wqkv, 3, dims, st, boxt, CU_TENSOR_MAP_SWIZZLE_32B);
  }
  {
    const cuuint64_t dims[3] = {64, 2048, 10}, st[2] = {1280, 128};
    const cuuint32_t boxk[3] = {64, 35, 1}, boxv[3] = {64, 32, 1};
    encode(fn, &m.k, p.k, 3, dims, st, boxk, CU_TENSOR_MAP_SWIZZLE_128B);
    encode(fn, &m.v, p.v, 3, dims, st, boxv, CU_TENSOR_MAP_SWIZZLE_128B);
  }
  {
    const cuuint64_t dims[3] = {16, 640, 40}, st[2] = {1280, 32};
    const cuuint32_t box[3] = {16, 40, 5};
    encode(fn, &m.wo, p.wo, 3, dims, st, box, CU_TENSOR_MAP_SWIZZLE_32B);
  }
  {
    const cuuint64_t dims[2] = {2048, 640}, st[1] = {U_PITCH * 16};
    const cuuint32_t box[2] = {64, 80};
    encode(fn, &m.y, yaddr, 2, dims, st, box, CU_TENSOR_MAP_SWIZZLE_128B);
    const cuuint64_t dl[2] = {64, DIM * U_PITCH / 8}, dol[2] = {64, NCTA * 160}, sl[1] = {128};
    const cuuint32_t bl[2] = {16, 32}, bol[2] = {16, 160};
    encode(fn, &m.yl, yaddr, 2, dl, sl, bl, CU_TENSOR_MAP_SWIZZLE_NONE);
    encode(fn, &m.ol, oaddr, 2, dol, sl, bol, CU_TENSOR_MAP_SWIZZLE_NONE);
  }
  {
    const cuuint64_t dims[2] = {640, 2048}, st[1] = {1280};
    const cuuint32_t bqm[2] = {64, 128}, bqt[2] = {16, 128}, bom[2] = {64, 16}, bot[2] = {16, 16};
    encode(fn, &m.qm, p.q, 2, dims, st, bqm, CU_TENSOR_MAP_SWIZZLE_128B);
    encode(fn, &m.qt, p.q, 2, dims, st, bqt, CU_TENSOR_MAP_SWIZZLE_32B);
    encode(fn, &m.om, p.out, 2, dims, st, bom, CU_TENSOR_MAP_SWIZZLE_128B);
    encode(fn, &m.ot, p.out, 2, dims, st, bot, CU_TENSOR_MAP_SWIZZLE_32B);
  }
  fused_kernel<<<NCTA, NTHR, SMEM_BYTES>>>(m, p);
}
```

```cpp
#include <cuda.h>
#include <cuda_bf16.h>
#include <cuda_runtime.h>
#include <stdint.h>

namespace {

constexpr int SEQ = 2048, DIM = 640, NCTA = 128, NTHR = 512;

#define TRIG_KB 9
#define KV_KB 2
#define DEV_EXIT 0
#define FENCE_LO 0
#define FENCE_HI 0
#define WB_TRIG B_USIG
#define T_ISSUE 256
#define RB32 3
#define WO_SKIP 1
#define WO_E0 1
#define WO_E1 0
#define T_INIT 448
#define TASK0 0x3
#define TASK1 0x52
#define TASK2 0x41
#define WL_TRIG B_WOP

constexpr uint32_t STAGE_BYTES = 47104, ST_W = 16384, ST_WT = 40960;
constexpr uint32_t O_BYTES = 20480, WO_BYTES = 12800;
constexpr uint32_t OFF_OA = 0;
constexpr uint32_t OFF_QS = 3 * O_BYTES, OFF_QT = OFF_QS + 16384;
constexpr uint32_t OFF_WC = 81920;
constexpr uint32_t OFF_WA = 94720;
constexpr uint32_t OFF_GATE = 145920;
constexpr uint32_t OFF_TT = 146432;
constexpr uint32_t OFF_KVX = 148480;
constexpr uint32_t OFF_CH3 = 163840;
constexpr uint32_t CH_BYTES = 12288, U_BYTES = 4096;
constexpr uint32_t OFF_FT = 225280, OFF_GT = 229376;
constexpr uint32_t OFF_CH0 = 188416;
constexpr uint32_t OFF_KVS = OFF_CH0, KVS_V = 4480, KVS_BYTES = 8576;
constexpr uint32_t OFF_YT = 163840;
constexpr uint32_t OFF_BAR = 231936;
constexpr uint32_t SMEM_BYTES = OFF_BAR + 512;

enum : uint32_t {
  B_EMPTY1 = 0, B_S3 = 3, B_E3 = 4, B_EMPTY2 = 5, B_ATTN = 9, B_P1 = 10,
  B_GATE = 11, B_HA = 12, B_KVD = 13, B_PREP = 14, B_YST = 15,
  B_CVD = 20,
  B_FULL2 = 21, B_U = 29, B_KV = 33, B_HB = 38, B_C34 = 39, B_YRB = 40, B_YFULL = 41, B_EPOCH = 42, B_LAST = 43, B_OSIG = 44,
  B_WOP = 45, B_USIG = 46, B_WST = 47, B_QF = 48, B_ORB = 49, B_YSIG = 50,
  B_F0 = 51, B_FULL1 = 52
};
constexpr uint32_t OFF_EPOCH = OFF_BAR + 8 * 58, OFF_D = OFF_BAR + 8 * 60;
__device__ __forceinline__ uint32_t off_o(int j) { return j < 4 ? OFF_OA + j * O_BYTES : j < 6 ? OFF_CH0 + (j - 4) * O_BYTES : OFF_OA + (j - 6) * O_BYTES; }
__device__ __forceinline__ uint32_t off_w(int j) { return j < 4 ? OFF_WA + j * WO_BYTES : j == 4 ? OFF_KVX : j == 5 ? OFF_WC : OFF_WA + (j - 6) * WO_BYTES; }
__device__ __forceinline__ int step_src(int hg, int j) { return j == 0 ? hg : j <= hg ? j - 1 : j; }
__device__ __forceinline__ bool tail_first(int hg) { return (hg & 3) == 3; }
__device__ __forceinline__ uint32_t off_ch(int c) { return (c < 3 ? OFF_CH0 : OFF_CH3 - 3 * CH_BYTES) + c * CH_BYTES; }

#define U_PITCH 264
__device__ __align__(1024) uint4 g_U[DIM * U_PITCH];
__device__ __align__(128) uint4 g_O[NCTA * 1280];
__device__ uint4 g_WO[64 * 800];
__device__ uint4 g_halo[NCTA * 2 * 7 * 32];
__device__ __align__(128) float g_gate[SEQ];
__device__ unsigned g_cnt[32 * (1 + 2 * 16 + 8 + NCTA)];
constexpr int C_LAUNCH = 0, C_PREP = 32, C_Y = 32 * 17, C_W = 32 * 33, C_O = 32 * 41;

#define TSM(cond, slot) do { } while (0)
#define TSIF(cond, slot) do { if (__LINE__ >= FENCE_LO && __LINE__ < FENCE_HI) sched_fence(); } while (0)
__device__ __forceinline__ void sched_fence() {
  asm volatile("{\n.reg .pred p;\n.reg .u32 c;\nmov.u32 c, %%clock;\nsetp.eq.u32 p, c, 0;\n@p st.shared.u32 [%0], c;\n}"
               ::"r"(1024 + OFF_EPOCH + 4) : "memory");
}
#define TS(slot) TSIF(true, slot)

struct Params {
  const __nv_bfloat16 *q, *k, *v, *shift_k, *ssm_k, *ssm_D, *wqkv, *wo, *gate_w;
  __nv_bfloat16* out;
  uint32_t zero;
};

constexpr int SPIN_LIMIT = 1 << 17;

__device__ __forceinline__ void mbar_init(uint32_t bar, uint32_t count) {
  asm volatile("mbarrier.init.shared::cta.b64 [%0], %1;" ::"r"(bar), "r"(count) : "memory");
}
__device__ __forceinline__ void mbar_expect_tx(uint32_t bar, uint32_t bytes) {
  asm volatile("mbarrier.arrive.expect_tx.shared::cta.b64 _, [%0], %1;" ::"r"(bar), "r"(bytes) : "memory");
}
__device__ __forceinline__ void mbar_arrive(uint32_t bar) {
  asm volatile("mbarrier.arrive.shared::cta.b64 _, [%0];" ::"r"(bar) : "memory");
}
__device__ __forceinline__ void mbar_wait(uint32_t bar, uint32_t parity) {
  uint32_t ok;
  int spins = 0;
  do {
      asm volatile("{\n.reg .pred p;\nmbarrier.try_wait.parity.shared::cta.b64 p, [%1], %2;\nselp.b32 %0, 1, 0, p;\n}"
                   : "=r"(ok) : "r"(bar), "r"(parity) : "memory");
    if (++spins > SPIN_LIMIT) break;
  } while (!ok);
}
__device__ __forceinline__ unsigned flag_read(const unsigned* p) {
  unsigned v;
  asm volatile("ld.relaxed.gpu.global.u32 %0, [%1];" : "=r"(v) : "l"(p) : "memory");
  return v;
}
__device__ __forceinline__ void flag_poll(const unsigned* p, unsigned target) {
  unsigned v;
  int spins = 0;
  do {
    asm volatile("ld.relaxed.gpu.global.u32 %0, [%1];" : "=r"(v) : "l"(p) : "memory");
    if (++spins > SPIN_LIMIT) break;
  } while ((int)(v - target) < 0);
}
__device__ __forceinline__ void flag_wait(const unsigned* p, unsigned target) {
  flag_poll(p, target);
}
__device__ __forceinline__ void flag_signal(unsigned* p, int n, int lane) {
  if (lane == 0) asm volatile("fence.release.gpu;" ::: "memory");
  __syncwarp();
  if (lane < n) asm volatile("red.relaxed.gpu.global.add.u32 [%0], 1;" ::"l"(p + 32 * lane) : "memory");
}
__device__ __forceinline__ void flag_bump(unsigned* p) {
  asm volatile("red.relaxed.gpu.global.add.u32 [%0], 1;" ::"l"(p) : "memory");
}
__device__ __forceinline__ void fence_async_smem() { asm volatile("fence.proxy.async.shared::cta;" ::: "memory"); }
__device__ __forceinline__ void wg_sync(int id) { asm volatile("bar.sync %0, 128;" ::"r"(id) : "memory"); }

__device__ __forceinline__ void tma_2d(uint32_t dst, const CUtensorMap* tm, int c0, int c1, uint32_t bar) {
  asm volatile("cp.async.bulk.tensor.2d.shared::cluster.global.mbarrier::complete_tx::bytes [%0], [%1, {%3, %4}], [%2];"
               ::"r"(dst), "l"(tm), "r"(bar), "r"(c0), "r"(c1) : "memory");
}
__device__ __forceinline__ void tma_3d(uint32_t dst, const CUtensorMap* tm, int c0, int c1, int c2, uint32_t bar) {
  asm volatile("cp.async.bulk.tensor.3d.shared::cluster.global.mbarrier::complete_tx::bytes [%0], [%1, {%3, %4, %5}], [%2];"
               ::"r"(dst), "l"(tm), "r"(bar), "r"(c0), "r"(c1), "r"(c2) : "memory");
}
__device__ __forceinline__ void bulk_load(uint32_t dst, const void* src, uint32_t bytes, uint32_t bar) {
  asm volatile("cp.async.bulk.shared::cluster.global.mbarrier::complete_tx::bytes [%0], [%1], %2, [%3];"
               ::"r"(dst), "l"(src), "r"(bytes), "r"(bar) : "memory");
}
__device__ __forceinline__ void bulk_store(void* dst, uint32_t src, uint32_t bytes) {
  asm volatile("cp.async.bulk.global.shared::cta.bulk_group [%0], [%1], %2;" ::"l"(dst), "r"(src), "r"(bytes) : "memory");
}
__device__ __forceinline__ void bulk_wait_read() {
  asm volatile("cp.async.bulk.commit_group;\ncp.async.bulk.wait_group.read 0;" ::: "memory");
}

__device__ __forceinline__ void publish(void* dst, uint32_t src, uint32_t bytes, uint32_t bar) {
  bulk_store(dst, src, bytes);
  bulk_wait_read();
  bulk_load(src, dst, bytes, bar);
}

__device__ __forceinline__ void wg_fence() { asm volatile("wgmma.fence.sync.aligned;" ::: "memory"); }
__device__ __forceinline__ void wg_commit() { asm volatile("wgmma.commit_group.sync.aligned;" ::: "memory"); }
template <int N> __device__ __forceinline__ void wg_wait() { asm volatile("wgmma.wait_group.sync.aligned %0;" ::"n"(N) : "memory"); }
__device__ __forceinline__ uint32_t desc_lo(uint32_t addr, uint32_t lbo) { return ((addr & 0x3FFFF) >> 4) | ((lbo >> 4) << 16); }
constexpr uint32_t desc_hi(uint32_t sbo, uint32_t swz) { return (sbo >> 4) | (swz << 30); }
constexpr uint32_t HI_SW128 = desc_hi(1024, 1), HI_SW64 = desc_hi(512, 2), HI_SW32 = desc_hi(256, 3), HI_NONE = desc_hi(128, 0);
template <int N> __device__ __forceinline__ void pin(float* d) {
#pragma unroll
  for (int i = 0; i < N; i++) asm volatile("" : "+f"(d[i])::"memory");
}

__device__ __forceinline__ uint32_t lds32(uint32_t a) {
  uint32_t v;
  asm volatile("ld.volatile.shared.u32 %0, [%1];" : "=r"(v) : "r"(a) : "memory");
  return v;
}
__device__ __forceinline__ uint2 ldg64(const void* a) {
  uint2 v;
  asm volatile("ld.global.nc.v2.u32 {%0, %1}, [%2];" : "=r"(v.x), "=r"(v.y) : "l"(a) : "memory");
  return v;
}
__device__ __forceinline__ void ldsm4(uint32_t* r, uint32_t a) {
  asm volatile("ldmatrix.sync.aligned.m8n8.x4.shared.b16 {%0, %1, %2, %3}, [%4];"
               : "=r"(r[0]), "=r"(r[1]), "=r"(r[2]), "=r"(r[3]) : "r"(a) : "memory");
}
__device__ __forceinline__ void ldsm4t(uint32_t* r, uint32_t a) {
  asm volatile("ldmatrix.sync.aligned.m8n8.x4.trans.shared.b16 {%0, %1, %2, %3}, [%4];"
               : "=r"(r[0]), "=r"(r[1]), "=r"(r[2]), "=r"(r[3]) : "r"(a) : "memory");
}
__device__ __forceinline__ uint2 lds64(uint32_t a) {
  uint2 v;
  asm volatile("ld.shared.v2.u32 {%0, %1}, [%2];" : "=r"(v.x), "=r"(v.y) : "r"(a) : "memory");
  return v;
}
__device__ __forceinline__ uint4 lds128(uint32_t a) {
  uint4 v;
  asm volatile("ld.shared.v4.u32 {%0, %1, %2, %3}, [%4];" : "=r"(v.x), "=r"(v.y), "=r"(v.z), "=r"(v.w) : "r"(a) : "memory");
  return v;
}
__device__ __forceinline__ void sts128(uint32_t a, uint32_t x, uint32_t y, uint32_t z, uint32_t w) {
  asm volatile("st.shared.v4.u32 [%0], {%1, %2, %3, %4};" ::"r"(a), "r"(x), "r"(y), "r"(z), "r"(w) : "memory");
}
__device__ __forceinline__ void stsm4(uint32_t a, const uint32_t* r) {
  asm volatile("stmatrix.sync.aligned.m8n8.x4.shared.b16 [%0], {%1, %2, %3, %4};" ::"r"(a), "r"(r[0]), "r"(r[1]), "r"(r[2]), "r"(r[3]) : "memory");
}
__device__ __forceinline__ uint32_t pack2(float lo, float hi) {
  uint32_t r;
  asm("cvt.rn.bf16x2.f32 %0, %1, %2;" : "=r"(r) : "f"(hi), "f"(lo));
  return r;
}
__device__ __forceinline__ uint32_t movm(uint32_t a) {
  uint32_t d;
  asm volatile("movmatrix.sync.aligned.m8n8.trans.b16 %0, %1;" : "=r"(d) : "r"(a));
  return d;
}
__device__ __forceinline__ uint32_t bmul(uint32_t a, uint32_t b) {
  uint32_t d;
  asm("mul.rn.bf16x2 %0, %1, %2;" : "=r"(d) : "r"(a), "r"(b));
  return d;
}
__device__ __forceinline__ uint32_t badd(uint32_t a, uint32_t b) {
  uint32_t d;
  asm("add.rn.bf16x2 %0, %1, %2;" : "=r"(d) : "r"(a), "r"(b));
  return d;
}
__device__ __forceinline__ uint32_t bfma(uint32_t a, uint32_t b, uint32_t c) {
  uint32_t d;
  asm("fma.rn.bf16x2 %0, %1, %2, %3;" : "=r"(d) : "r"(a), "r"(b), "r"(c));
  return d;
}
__device__ __forceinline__ float bf_lo(uint32_t x) { return __uint_as_float(x << 16); }
__device__ __forceinline__ float bf_hi(uint32_t x) { return __uint_as_float(x & 0xFFFF0000u); }
__device__ __forceinline__ float ex2(float x) {
  float y;
  asm("ex2.approx.ftz.f32 %0, %1;" : "=f"(y) : "f"(x));
  return y;
}
__device__ __forceinline__ float rcp(float x) {
  float y;
  asm("rcp.approx.ftz.f32 %0, %1;" : "=f"(y) : "f"(x));
  return y;
}
__device__ __forceinline__ void mma16816(float* d, uint32_t a0, uint32_t a1, uint32_t a2, uint32_t a3, uint32_t b0, uint32_t b1) {
  asm volatile("mma.sync.aligned.m16n8k16.row.col.f32.bf16.bf16.f32 {%0, %1, %2, %3}, {%4, %5, %6, %7}, {%8, %9}, {%0, %1, %2, %3};"
               : "+f"(d[0]), "+f"(d[1]), "+f"(d[2]), "+f"(d[3])
               : "r"(a0), "r"(a1), "r"(a2), "r"(a3), "r"(b0), "r"(b1));
}
__device__ __forceinline__ void mma1688(float* d, uint32_t a0, uint32_t a1, uint32_t b0) {
  asm volatile("mma.sync.aligned.m16n8k8.row.col.f32.bf16.bf16.f32 {%0, %1, %2, %3}, {%4, %5}, {%6}, {%0, %1, %2, %3};"
               : "+f"(d[0]), "+f"(d[1]), "+f"(d[2]), "+f"(d[3])
               : "r"(a0), "r"(a1), "r"(b0));
}

template <int N> struct WgRS;
template <int N> struct WgSST;
template <> struct WgRS<32> {
  template <uint32_t HB>
  static __device__ __forceinline__ void mma(float* d, const uint32_t* a, uint32_t db) {
    asm volatile("{\n.reg .pred p;\n.reg .b64 db;\nsetp.ne.b32 p, %22, 0;\n"
      "mov.b64 db, {%20, %21};\n"
      "wgmma.mma_async.sync.aligned.m64n32k16.f32.bf16.bf16 {"
      "%0, %1, %2, %3, %4, %5, %6, %7, %8, %9, %10, %11, %12, %13, %14, %15"
      "}, {%16, %17, %18, %19}, db, p, 1, 1, 1;\n}\n"
      : "+f"(d[0]), "+f"(d[1]), "+f"(d[2]), "+f"(d[3]), "+f"(d[4]), "+f"(d[5]), "+f"(d[6]), "+f"(d[7]),
        "+f"(d[8]), "+f"(d[9]), "+f"(d[10]), "+f"(d[11]), "+f"(d[12]), "+f"(d[13]), "+f"(d[14]), "+f"(d[15])
      : "r"(a[0]), "r"(a[1]), "r"(a[2]), "r"(a[3]), "r"(db), "n"(HB), "n"(1));
  }
  template <uint32_t HB>
  static __device__ __forceinline__ void set(float* d, const uint32_t* a, uint32_t db) {
    asm volatile("{\n.reg .pred p;\n.reg .b64 db;\nsetp.ne.b32 p, %22, 0;\n"
      "mov.b64 db, {%20, %21};\n"
      "wgmma.mma_async.sync.aligned.m64n32k16.f32.bf16.bf16 {"
      "%0, %1, %2, %3, %4, %5, %6, %7, %8, %9, %10, %11, %12, %13, %14, %15"
      "}, {%16, %17, %18, %19}, db, p, 1, 1, 1;\n}\n"
      : "=f"(d[0]), "=f"(d[1]), "=f"(d[2]), "=f"(d[3]), "=f"(d[4]), "=f"(d[5]), "=f"(d[6]), "=f"(d[7]),
        "=f"(d[8]), "=f"(d[9]), "=f"(d[10]), "=f"(d[11]), "=f"(d[12]), "=f"(d[13]), "=f"(d[14]), "=f"(d[15])
      : "r"(a[0]), "r"(a[1]), "r"(a[2]), "r"(a[3]), "r"(db), "n"(HB), "n"(0));
  }
};
template <> struct WgRS<64> {
  template <uint32_t HB>
  static __device__ __forceinline__ void mma(float* d, const uint32_t* a, uint32_t db) {
    asm volatile("{\n.reg .pred p;\n.reg .b64 db;\nsetp.ne.b32 p, %38, 0;\n"
      "mov.b64 db, {%36, %37};\n"
      "wgmma.mma_async.sync.aligned.m64n64k16.f32.bf16.bf16 {"
      "%0, %1, %2, %3, %4, %5, %6, %7, %8, %9, %10, %11, %12, %13, %14, %15, "
      "%16, %17, %18, %19, %20, %21, %22, %23, %24, %25, %26, %27, %28, %29, %30, %31"
      "}, {%32, %33, %34, %35}, db, p, 1, 1, 1;\n}\n"
      : "+f"(d[0]), "+f"(d[1]), "+f"(d[2]), "+f"(d[3]), "+f"(d[4]), "+f"(d[5]), "+f"(d[6]), "+f"(d[7]),
        "+f"(d[8]), "+f"(d[9]), "+f"(d[10]), "+f"(d[11]), "+f"(d[12]), "+f"(d[13]), "+f"(d[14]), "+f"(d[15]),
        "+f"(d[16]), "+f"(d[17]), "+f"(d[18]), "+f"(d[19]), "+f"(d[20]), "+f"(d[21]), "+f"(d[22]), "+f"(d[23]),
        "+f"(d[24]), "+f"(d[25]), "+f"(d[26]), "+f"(d[27]), "+f"(d[28]), "+f"(d[29]), "+f"(d[30]), "+f"(d[31])
      : "r"(a[0]), "r"(a[1]), "r"(a[2]), "r"(a[3]), "r"(db), "n"(HB), "n"(1));
  }
  template <uint32_t HB>
  static __device__ __forceinline__ void set(float* d, const uint32_t* a, uint32_t db) {
    asm volatile("{\n.reg .pred p;\n.reg .b64 db;\nsetp.ne.b32 p, %38, 0;\n"
      "mov.b64 db, {%36, %37};\n"
      "wgmma.mma_async.sync.aligned.m64n64k16.f32.bf16.bf16 {"
      "%0, %1, %2, %3, %4, %5, %6, %7, %8, %9, %10, %11, %12, %13, %14, %15, "
      "%16, %17, %18, %19, %20, %21, %22, %23, %24, %25, %26, %27, %28, %29, %30, %31"
      "}, {%32, %33, %34, %35}, db, p, 1, 1, 1;\n}\n"
      : "=f"(d[0]), "=f"(d[1]), "=f"(d[2]), "=f"(d[3]), "=f"(d[4]), "=f"(d[5]), "=f"(d[6]), "=f"(d[7]),
        "=f"(d[8]), "=f"(d[9]), "=f"(d[10]), "=f"(d[11]), "=f"(d[12]), "=f"(d[13]), "=f"(d[14]), "=f"(d[15]),
        "=f"(d[16]), "=f"(d[17]), "=f"(d[18]), "=f"(d[19]), "=f"(d[20]), "=f"(d[21]), "=f"(d[22]), "=f"(d[23]),
        "=f"(d[24]), "=f"(d[25]), "=f"(d[26]), "=f"(d[27]), "=f"(d[28]), "=f"(d[29]), "=f"(d[30]), "=f"(d[31])
      : "r"(a[0]), "r"(a[1]), "r"(a[2]), "r"(a[3]), "r"(db), "n"(HB), "n"(0));
  }
};
template <> struct WgSST<48> {
  template <uint32_t HA, uint32_t HB>
  static __device__ __forceinline__ void mma(float* d, uint32_t da, uint32_t db, int sc) {
    asm volatile("{\n.reg .pred p;\n.reg .b64 da, db;\nsetp.ne.b32 p, %28, 0;\n"
      "mov.b64 da, {%24, %25};\nmov.b64 db, {%26, %27};\n"
      "wgmma.mma_async.sync.aligned.m64n48k16.f32.bf16.bf16 {"
      "%0, %1, %2, %3, %4, %5, %6, %7, %8, %9, %10, %11, %12, %13, %14, %15, "
      "%16, %17, %18, %19, %20, %21, %22, %23"
      "}, da, db, p, 1, 1, 0, 1;\n}\n"
      : "+f"(d[0]), "+f"(d[1]), "+f"(d[2]), "+f"(d[3]), "+f"(d[4]), "+f"(d[5]), "+f"(d[6]), "+f"(d[7]),
        "+f"(d[8]), "+f"(d[9]), "+f"(d[10]), "+f"(d[11]), "+f"(d[12]), "+f"(d[13]), "+f"(d[14]), "+f"(d[15]),
        "+f"(d[16]), "+f"(d[17]), "+f"(d[18]), "+f"(d[19]), "+f"(d[20]), "+f"(d[21]), "+f"(d[22]), "+f"(d[23])
      : "r"(da), "n"(HA), "r"(db), "n"(HB), "r"(sc));
  }
};
template <> struct WgSST<80> {
  template <uint32_t HA, uint32_t HB>
  static __device__ __forceinline__ void mma(float* d, uint32_t da, uint32_t db, int sc) {
    asm volatile("{\n.reg .pred p;\n.reg .b64 da, db;\nsetp.ne.b32 p, %44, 0;\n"
      "mov.b64 da, {%40, %41};\nmov.b64 db, {%42, %43};\n"
      "wgmma.mma_async.sync.aligned.m64n80k16.f32.bf16.bf16 {"
      "%0, %1, %2, %3, %4, %5, %6, %7, %8, %9, %10, %11, %12, %13, %14, %15, "
      "%16, %17, %18, %19, %20, %21, %22, %23, %24, %25, %26, %27, %28, %29, %30, %31, "
      "%32, %33, %34, %35, %36, %37, %38, %39"
      "}, da, db, p, 1, 1, 0, 1;\n}\n"
      : "+f"(d[0]), "+f"(d[1]), "+f"(d[2]), "+f"(d[3]), "+f"(d[4]), "+f"(d[5]), "+f"(d[6]), "+f"(d[7]),
        "+f"(d[8]), "+f"(d[9]), "+f"(d[10]), "+f"(d[11]), "+f"(d[12]), "+f"(d[13]), "+f"(d[14]), "+f"(d[15]),
        "+f"(d[16]), "+f"(d[17]), "+f"(d[18]), "+f"(d[19]), "+f"(d[20]), "+f"(d[21]), "+f"(d[22]), "+f"(d[23]),
        "+f"(d[24]), "+f"(d[25]), "+f"(d[26]), "+f"(d[27]), "+f"(d[28]), "+f"(d[29]), "+f"(d[30]), "+f"(d[31]),
        "+f"(d[32]), "+f"(d[33]), "+f"(d[34]), "+f"(d[35]), "+f"(d[36]), "+f"(d[37]), "+f"(d[38]), "+f"(d[39])
      : "r"(da), "n"(HA), "r"(db), "n"(HB), "r"(sc));
  }
};
template <> struct WgSST<192> {
  template <uint32_t HA, uint32_t HB>
  static __device__ __forceinline__ void mma(float* d, uint32_t da, uint32_t db, int sc) {
    asm volatile("{\n.reg .pred p;\n.reg .b64 da, db;\nsetp.ne.b32 p, %100, 0;\n"
      "mov.b64 da, {%96, %97};\nmov.b64 db, {%98, %99};\n"
      "wgmma.mma_async.sync.aligned.m64n192k16.f32.bf16.bf16 {"
      "%0, %1, %2, %3, %4, %5, %6, %7, %8, %9, %10, %11, %12, %13, %14, %15, "
      "%16, %17, %18, %19, %20, %21, %22, %23, %24, %25, %26, %27, %28, %29, %30, %31, "
      "%32, %33, %34, %35, %36, %37, %38, %39, %40, %41, %42, %43, %44, %45, %46, %47, "
      "%48, %49, %50, %51, %52, %53, %54, %55, %56, %57, %58, %59, %60, %61, %62, %63, "
      "%64, %65, %66, %67, %68, %69, %70, %71, %72, %73, %74, %75, %76, %77, %78, %79, "
      "%80, %81, %82, %83, %84, %85, %86, %87, %88, %89, %90, %91, %92, %93, %94, %95"
      "}, da, db, p, 1, 1, 0, 1;\n}\n"
      : "+f"(d[0]), "+f"(d[1]), "+f"(d[2]), "+f"(d[3]), "+f"(d[4]), "+f"(d[5]), "+f"(d[6]), "+f"(d[7]),
        "+f"(d[8]), "+f"(d[9]), "+f"(d[10]), "+f"(d[11]), "+f"(d[12]), "+f"(d[13]), "+f"(d[14]), "+f"(d[15]),
        "+f"(d[16]), "+f"(d[17]), "+f"(d[18]), "+f"(d[19]), "+f"(d[20]), "+f"(d[21]), "+f"(d[22]), "+f"(d[23]),
        "+f"(d[24]), "+f"(d[25]), "+f"(d[26]), "+f"(d[27]), "+f"(d[28]), "+f"(d[29]), "+f"(d[30]), "+f"(d[31]),
        "+f"(d[32]), "+f"(d[33]), "+f"(d[34]), "+f"(d[35]), "+f"(d[36]), "+f"(d[37]), "+f"(d[38]), "+f"(d[39]),
        "+f"(d[40]), "+f"(d[41]), "+f"(d[42]), "+f"(d[43]), "+f"(d[44]), "+f"(d[45]), "+f"(d[46]), "+f"(d[47]),
        "+f"(d[48]), "+f"(d[49]), "+f"(d[50]), "+f"(d[51]), "+f"(d[52]), "+f"(d[53]), "+f"(d[54]), "+f"(d[55]),
        "+f"(d[56]), "+f"(d[57]), "+f"(d[58]), "+f"(d[59]), "+f"(d[60]), "+f"(d[61]), "+f"(d[62]), "+f"(d[63]),
        "+f"(d[64]), "+f"(d[65]), "+f"(d[66]), "+f"(d[67]), "+f"(d[68]), "+f"(d[69]), "+f"(d[70]), "+f"(d[71]),
        "+f"(d[72]), "+f"(d[73]), "+f"(d[74]), "+f"(d[75]), "+f"(d[76]), "+f"(d[77]), "+f"(d[78]), "+f"(d[79]),
        "+f"(d[80]), "+f"(d[81]), "+f"(d[82]), "+f"(d[83]), "+f"(d[84]), "+f"(d[85]), "+f"(d[86]), "+f"(d[87]),
        "+f"(d[88]), "+f"(d[89]), "+f"(d[90]), "+f"(d[91]), "+f"(d[92]), "+f"(d[93]), "+f"(d[94]), "+f"(d[95])
      : "r"(da), "n"(HA), "r"(db), "n"(HB), "r"(sc));
  }
};

struct FftConst {
  uint32_t f[2][4], fi[4][4];
  uint32_t ta[2][2], tb[2][2];
};
__device__ __forceinline__ void cis(int m, float scale, float& c, float& s) {
  const float a = (float)m * (-6.283185307179586f * scale);
  c = __cosf(a);
  s = __sinf(a);
}
__device__ __forceinline__ void fft_tables(uint32_t (&v)[12], int tw) {
  const int row = tw >> 2, ch = tw & 3;
#pragma unroll
  for (int i = 0; i < 4; i++) {
    float c[2], s[2], x[2];
#pragma unroll
    for (int e = 0; e < 2; e++) {
      cis((((32 * (8 * ch + 2 * i + e) + 15) * (4 * row - 63) + 2048) & 4095) - 2048, 1.f / 4096, c[e], s[e]);
      float gc, gs;
      cis((((row & 15) * (8 * (ch & 1) + 2 * i + e) + 8) & 15) - 8, 1.f / 16, gc, gs);
      x[e] = (row >> 4) == (ch >> 1) ? gc : (ch >> 1) ? gs : -gs;
    }
    v[i] = pack2(c[0] * 0.125f, c[1] * 0.125f);
    v[4 + i] = pack2(s[0] * 0.125f, s[1] * 0.125f);
    v[8 + i] = pack2(x[0], x[1]);
  }
#pragma unroll
  for (int i = 0; i < 12; i++) asm volatile("" : "+r"(v[i]));
}
__device__ __forceinline__ void fft_tables_store(const uint32_t (&v)[12], uint32_t sb, int tw) {
  const int row = tw >> 2;
  const uint32_t x = ((tw ^ (row >> 1)) & 3) << 4, a = sb + OFF_FT + (16 * (row >> 3) + (row & 7)) * 64 + x;
  sts128(a, v[0], v[1], v[2], v[3]);
  sts128(a + 512, v[4], v[5], v[6], v[7]);
  sts128(sb + OFF_GT + row * 64 + x, v[8], v[9], v[10], v[11]);
}
__device__ __forceinline__ void fft_twiddles(uint32_t (&v)[2], int tw) {
  float a[2], s[2];
#pragma unroll
  for (int i = 0; i < 2; i++) {
    float c;
    cis((2 * (2 * (tw & 3) + i) - 15) * (4 * (tw >> 2) - 63), 1.f / 4096, c, s[i]);
    a[i] = __fdividef(-s[i], 1.f + c);
  }
  v[0] = pack2(a[0], a[1]);
  v[1] = pack2(s[0], s[1]);
  asm volatile("" : "+r"(v[0]), "+r"(v[1]));
}
__device__ __forceinline__ void fft_matrices(FftConst& k, uint32_t sb, int w, int lane) {
  const uint32_t x = (lane >> 1) & 3;
  const uint2 t0 = lds64(sb + OFF_TT + 256 * w + 8 * lane), t1 = lds64(sb + OFF_TT + 256 * w + 8 * (lane ^ 3));
  k.ta[0][0] = t0.x;
  k.tb[0][0] = t0.y;
  k.ta[1][1] = __byte_perm(t1.x, 0, 0x1032);
  k.tb[1][1] = __byte_perm(t1.y, 0, 0x1032);
#pragma unroll
  for (int j = 0; j < 2; j++) {
    k.ta[1 - j][j] = k.ta[j][j] ^ 0x80008000u;
    k.tb[1 - j][j] = k.tb[j][j] ^ 0x80008000u;
    asm volatile("" : "+r"(k.ta[0][j]), "+r"(k.tb[0][j]), "+r"(k.ta[1][j]), "+r"(k.tb[1][j]));
  }
#pragma unroll
  for (int i = 0; i < 2; i++) {
    ldsm4(k.f[i], sb + OFF_FT + (16 * w + (lane & 15)) * 64 + (((2 * i + (lane >> 4)) ^ x) << 4));
    ldsm4t(k.fi[i], sb + OFF_FT + (32 * i + lane) * 64 + ((w ^ x) << 4));
#pragma unroll
    for (int j = 0; j < 4; j++) {
      k.fi[2 + i][j] = (j & 1) ? k.fi[i][j - 1] ^ 0x80008000u : k.fi[i][j + 1];
      asm volatile("" : "+r"(k.fi[2 + i][j]));
    }
  }
}
__device__ __forceinline__ void rot(uint32_t& x, uint32_t& y, uint32_t a, uint32_t b) {
  x = bfma(a, y, x);
  y = bfma(b, x, y);
  x = bfma(a, y, x);
}
__device__ __forceinline__ void twiddle_fwd(uint32_t (&a)[4][4], float* d, const FftConst& k) {
#pragma unroll
  for (int q = 0; q < 4; q++)
#pragma unroll
    for (int j = 0; j < 2; j++) {
      const float* x = d + 8 * q + 4 * j;
      uint32_t re = pack2(x[0], x[1]), im = pack2(x[2], x[3]);
      rot(re, im, k.ta[0][j], k.tb[0][j]);
      a[q & 2][2 * j + (q & 1)] = re;
      a[(q & 2) + 1][2 * j + (q & 1)] = im;
    }
}
__device__ __forceinline__ void g_step(float* d, const uint32_t (&a)[4][4], uint32_t dre, uint32_t dim) {
  WgRS<32>::set<HI_SW64>(d, a[0], dre);
  WgRS<32>::set<HI_SW64>(d + 16, a[2], dre);
  WgRS<32>::mma<HI_SW64>(d, a[1], dim);
  WgRS<32>::mma<HI_SW64>(d + 16, a[3], dim);
  wg_commit();
}

__device__ __forceinline__ void products(uint32_t (&a)[4][4], const float* H, const float* U, int p) {
#pragma unroll
  for (int j = 0; j < 2; j++)
#pragma unroll
    for (int m = 2 * p; m < 2 * p + 2; m++) {
      float pr[2], pi[2];
#pragma unroll
      for (int x = 0; x < 2; x++)
#pragma unroll
        for (int q = 0; q <= m; q++) {
          const int ih = 16 * (q >> 1) + 2 * (q & 1) + 4 * j + x, iu = 16 * ((m - q) >> 1) + 2 * ((m - q) & 1) + 4 * j + x;
          pr[x] = q ? fmaf(H[ih], U[iu], pr[x]) : H[ih] * U[iu];
          pi[x] = q ? fmaf(H[ih], U[iu + 8], pi[x]) : H[ih] * U[iu + 8];
          pr[x] = fmaf(-H[ih + 8], U[iu + 8], pr[x]);
          pi[x] = fmaf(H[ih + 8], U[iu], pi[x]);
        }
      a[m & 2][2 * j + (m & 1)] = pack2(pr[0], pr[1]);
      a[(m & 2) + 1][2 * j + (m & 1)] = pack2(pi[0], pi[1]);
    }
}

__device__ __forceinline__ void conv_channel(const FftConst& k, uint32_t sb, int c, int wg, int w, int lane) {
  const uint32_t cb = sb + off_ch(c), bars = sb + OFF_BAR;
  const uint32_t du = desc_lo(cb, 1024), dg = desc_lo(sb + OFF_GT, 16), dz = desc_lo(cb + U_BYTES, 16);
  float U[32], H[32];
  uint32_t a[4][4], e[4][4];
  const float dv = __uint_as_float(lds32(sb + OFF_D + 4 * c));
  wg_fence();
  WgRS<64>::set<HI_SW32>(H, k.f[0], du + 256);
  WgRS<64>::mma<HI_SW32>(H, k.f[1], du + 256 + 32);
  wg_commit();
  wg_wait<0>();
  pin<32>(H);
  twiddle_fwd(a, H, k);
  mbar_wait(bars + 8 * (B_U + (c < 3 ? c : 3)), 0);
  TSM(w == 0 && c < 3, 7 + wg);
  wg_fence();
  WgRS<64>::set<HI_SW32>(U, k.f[0], du);
  WgRS<64>::mma<HI_SW32>(U, k.f[1], du + 32);
  wg_commit();
  g_step(H, a, dg, dg + 64);
  wg_wait<1>();
  pin<32>(U);
  twiddle_fwd(e, U, k);
  wg_fence();
  g_step(U, e, dg, dg + 64);
  wg_wait<0>();
  pin<32>(U);
  pin<32>(H);
#pragma unroll
  for (int j = 0; j < 4; j++) H[4 * (j >> 1) + (j & 1)] += dv;
  float V[32];
#pragma unroll
  for (int p = 0; p < 2; p++) {
    products(a, H, U, p);
    wg_fence();
    WgRS<32>::set<HI_SW64>(V + 16 * p, a[2 * p], dg + 64);
    WgRS<32>::mma<HI_SW64>(V + 16 * p, a[2 * p + 1], dg);
    wg_commit();
  }
  const uint32_t za = cb + U_BYTES + (8 * w + (lane & 7)) * 128 + (((lane >> 3) ^ (lane & 7)) << 4);
  const uint32_t ya = cb + (lane >> 4) * 1024 + (8 * w + (lane & 7)) * 32 + ((((lane >> 3) ^ (lane >> 2)) & 1) << 4);
  wg_sync(1 + wg);
#pragma unroll
  for (int p = 0; p < 2; p++) {
    if (p == 0) wg_wait<1>();
    else wg_wait<0>();
    pin<16>(V + 16 * p);
#pragma unroll
    for (int i = 0; i < 4; i++) {
      const int j = i & 1;
      const float* x = V + 16 * p + 4 * j + (i & 2);
      e[p][i] = pack2(x[8], x[9]);
      e[2 + p][i] = pack2(x[0], x[1]);
      rot(e[p][i], e[2 + p][i], k.ta[1][j], k.tb[1][j]);
    }
    stsm4(za ^ (64 * p), e[p]);
    stsm4((za ^ (64 * p)) + 4096, e[2 + p]);
  }
  fence_async_smem();
  wg_sync(1 + wg);
  wg_fence();
  WgRS<64>::set<HI_SW128>(H, k.fi[0], dz);
#pragma unroll
  for (int ks = 1; ks < 4; ks++) WgRS<64>::mma<HI_SW128>(H, k.fi[ks], dz + 128 * ks);
  wg_commit();
  wg_wait<0>();
  pin<32>(H);
  if (lane == 0) mbar_arrive(bars + 8 * B_CVD);
  TSIF(w == 0, 88 + c);
#pragma unroll
  for (int j = 0; j < 8; j++)
    a[j >> 2][j & 3] = j < 2 ? pack2(H[4 * j], H[4 * j + 1]) : pack2(H[4 * j] + H[4 * j - 6], H[4 * j + 1] + H[4 * j - 5]);
  stsm4(ya, a[0]);
  stsm4(ya + 2048, a[1]);
  fence_async_smem();
  __syncwarp();
}

__device__ __forceinline__ void prep_slab(uint4* res, const uint2* sw, uint32_t sb, int slab, int w, int lane) {
  const int t = lane & 3, tp = (lane & 7) >> 1, pos = 8 * tp + 2 * (((lane >> 3) + tp) & 3) + (lane & 1);
  const uint32_t base = sb + OFF_KVS + slab * KVS_BYTES + pos * 128;
  uint32_t kk[2][4][4], vv[2][4];
  mbar_wait(sb + OFF_BAR + 8 * (B_KV + slab), 0);
#pragma unroll
  for (int h = 0; h < 2; h++) {
#pragma unroll
    for (int j = 0; j < 4; j++) {
      const uint32_t a = base + 128 * j;
      ldsm4t(kk[h][j], a + (((w + 4 * h) ^ ((a >> 7) & 7)) << 4));
    }
    const uint32_t a = base + KVS_V;
    ldsm4t(vv[h], a + (((w + 4 * h) ^ ((a >> 7) & 7)) << 4));
  }
#pragma unroll
  for (int h = 0; h < 2; h++) {
    uint32_t (&k)[4][4] = kk[h];
    uint32_t (&v)[4] = vv[h];
    const uint32_t w0 = __byte_perm(sw[h].x, 0, 0x1010), w1 = __byte_perm(sw[h].x, 0, 0x3232);
    const uint32_t w2 = __byte_perm(sw[h].y, 0, 0x1010), w3 = __byte_perm(sw[h].y, 0, 0x3232);
#pragma unroll
    for (int m = 0; m < 4; m++)
      v[m] = bmul(badd(badd(badd(bmul(k[0][m], w3), bmul(k[1][m], w2)), bmul(k[2][m], w1)), bmul(k[3][m], w0)), v[m]);
    uint32_t a[4];
#pragma unroll
    for (int m = 0; m < 4; m++) a[m] = (t & 1) ? v[(m + 3) & 3] : v[m];
    res[h] = (t & 2) ? make_uint4(a[2], a[3], a[0], a[1]) : make_uint4(a[0], a[1], a[2], a[3]);
  }
}

__device__ __forceinline__ void prep_gate(const Params& p, uint32_t sb, int b, int w, int lane) {
  uint2 gw[5], x[4][5];
#pragma unroll
  for (int j = 0; j < 5; j++) gw[j] = ldg64(reinterpret_cast<const uint2*>(p.gate_w) + lane + 32 * j);
#pragma unroll
  for (int i = 0; i < 4; i++)
#pragma unroll
    for (int j = 0; j < 5; j++)
      x[i][j] = ldg64(reinterpret_cast<const uint2*>(p.q) + (16 * b + 4 * w + i) * (DIM / 4) + lane + 32 * j);
  float s[4];
#pragma unroll
  for (int i = 0; i < 4; i++) {
    s[i] = 0.f;
#pragma unroll
    for (int j = 0; j < 5; j++) {
      const uint32_t m0 = bmul(x[i][j].x, gw[j].x), m1 = bmul(x[i][j].y, gw[j].y);
      s[i] += (bf_lo(m0) + bf_hi(m0)) + (bf_lo(m1) + bf_hi(m1));
    }
  }
  const bool h = lane & 16, q = lane & 8;
  const float a = (h ? s[2] : s[0]) + __shfl_xor_sync(0xffffffffu, h ? s[0] : s[2], 16);
  const float c = (h ? s[3] : s[1]) + __shfl_xor_sync(0xffffffffu, h ? s[1] : s[3], 16);
  float z = (q ? c : a) + __shfl_xor_sync(0xffffffffu, q ? a : c, 8);
#pragma unroll
  for (int o = 4; o > 0; o >>= 1) z += __shfl_xor_sync(0xffffffffu, z, o);
  z = bf_lo(pack2(z, 0.f));
  z = bf_lo(pack2(__fdividef(1.f, 1.f + __expf(-z)), 0.f));
  mbar_wait(sb + OFF_BAR + 8 * B_S3, 0);
  if ((lane & 7) == 0) asm volatile("st.shared.f32 [%0], %1;" ::"r"(sb + OFF_GATE + 64 * (b & 7) + 16 * w + (lane >> 1)), "f"(z) : "memory");
  fence_async_smem();
}

__device__ __forceinline__ uint32_t bmax(uint32_t a, uint32_t b) {
  uint32_t d;
  asm("max.bf16x2 %0, %1, %2;" : "=r"(d) : "r"(a), "r"(b));
  return d;
}
__device__ __forceinline__ void softmax_two(const float (&l)[2][2], uint32_t& p0, uint32_t& p1) {
  constexpr float kScale = 0.22360679774997896f, kLog2e = 1.4426950408889634f;
  const uint32_t r0 = pack2(l[0][0], l[1][0]), r1 = pack2(l[0][1], l[1][1]);
  const uint32_t x0 = pack2(bf_lo(r0) * kScale, bf_hi(r0) * kScale), x1 = pack2(bf_lo(r1) * kScale, bf_hi(r1) * kScale);
  uint32_t m = bmax(x0, x1);
  m = bmax(m, __shfl_xor_sync(0xffffffffu, m, 1));
  m = bmax(m, __shfl_xor_sync(0xffffffffu, m, 2));
  const float m0 = bf_lo(m) * kLog2e, m1 = bf_hi(m) * kLog2e;
  p0 = pack2(ex2(bf_lo(x0) * kLog2e - m0), ex2(bf_lo(x1) * kLog2e - m0));
  p1 = pack2(ex2(bf_hi(x0) * kLog2e - m1), ex2(bf_hi(x1) * kLog2e - m1));
}

__device__ __forceinline__ void halo_read(uint32_t (&kpv)[10], uint32_t (&vpv)[10], uint32_t (&tg)[7], const uint4* hp) {
#pragma unroll
  for (int j = 0; j < 7; j++) {
    uint32_t x0, x1, x2;
    asm volatile("ld.relaxed.gpu.global.v4.u32 {%0, %1, %2, %3}, [%4];"
                 : "=r"(x0), "=r"(x1), "=r"(x2), "=r"(tg[j]) : "l"(hp + 32 * j) : "memory");
    if (j < 4) kpv[3 * j] = x0; else vpv[3 * j - 10] = x0;
    if (j < 3) kpv[3 * j + 1] = x1; else vpv[3 * j - 9] = x1;
    if (j < 3) kpv[3 * j + 2] = x2; else if (j < 6) vpv[3 * j - 8] = x2;
  }
}

template <int ROT>
__device__ __forceinline__ void pack_qkv(const float* acc, uint32_t (&qlo)[10], uint32_t (&qhi)[10], uint32_t (&klo)[10],
                                         uint32_t (&khi)[10], uint32_t (&vlo)[10], uint32_t (&vhi)[10]) {
#pragma unroll
  for (int j = 0; j < 10; j++) {
    const int x = (j + ROT) % 10, tq = x < 8 ? x : 16 + x, tk = x < 8 ? 8 + x : 18 + x, tv = x < 8 ? 16 + x : 20 + x;
    khi[j] = pack2(acc[4 * tk + 2], acc[4 * tk + 3]);
    vhi[j] = movm(pack2(acc[4 * tv + 2], acc[4 * tv + 3]));
    qlo[j] = pack2(acc[4 * tq], acc[4 * tq + 1]);
    qhi[j] = pack2(acc[4 * tq + 2], acc[4 * tq + 3]);
    klo[j] = pack2(acc[4 * tk], acc[4 * tk + 1]);
    vlo[j] = pack2(acc[4 * tv], acc[4 * tv + 1]);
    asm volatile("" : "+r"(khi[j]), "+r"(qlo[j]), "+r"(qhi[j]), "+r"(klo[j]), "+r"(vlo[j]));
  }
}

template <int ROT> __device__ __forceinline__ void halo_send(const float* acc, uint4* ho, uint32_t tag) {
#pragma unroll
  for (int j = 0; j < 7; j++) {
    uint32_t x[3];
#pragma unroll
    for (int e = 0; e < 3; e++) {
      const int i = 3 * j + e, y = (i % 10 + ROT) % 10, tk = y < 8 ? 8 + y : 18 + y, tv = y < 8 ? 16 + y : 20 + y;
      x[e] = i < 10 ? pack2(acc[4 * tk + 2], acc[4 * tk + 3]) : i < 20 ? movm(pack2(acc[4 * tv + 2], acc[4 * tv + 3])) : 0u;
    }
    asm volatile("st.relaxed.gpu.global.v4.u32 [%0], {%1, %2, %3, %4};" ::"l"(ho + 32 * j), "r"(x[0]), "r"(x[1]), "r"(x[2]), "r"(tag) : "memory");
  }
}

__device__ __forceinline__ void attention(float* acc, uint32_t sb, int b, int par, int w, int lane, uint32_t tag) {
  const int g = lane >> 2, t = lane & 3;
  uint32_t klo[10], khi[10], vlo[10], vhi[10], qlo[10], qhi[10], kpv[10], vpv[10];
  if (w == 3 && b < NCTA - 8) {
    uint4* ho = g_halo + (b * 2 + par) * 224 + lane;
    if (tail_first(b & 7)) halo_send<8>(acc, ho, tag);
    else halo_send<0>(acc, ho, tag);
    TSIF(par == 0, 76);
    pin<120>(acc);
  }
  if (tail_first(b & 7)) pack_qkv<8>(acc, qlo, qhi, klo, khi, vlo, vhi);
  else pack_qkv<0>(acc, qlo, qhi, klo, khi, vlo, vhi);
  const uint32_t xa = sb + OFF_KVX + (par * 3) * 2560 + lane * 16;
  if (w < 3) {
    sts128(xa + w * 2560, khi[0], khi[1], khi[2], khi[3]);
    sts128(xa + w * 2560 + 512, khi[4], khi[5], khi[6], khi[7]);
    sts128(xa + w * 2560 + 1024, khi[8], khi[9], vhi[0], vhi[1]);
    sts128(xa + w * 2560 + 1536, vhi[2], vhi[3], vhi[4], vhi[5]);
    sts128(xa + w * 2560 + 2048, vhi[6], vhi[7], vhi[8], vhi[9]);
  }
  TSIF(par == 0 && w == 1, 64);
#pragma unroll
  for (int j = 0; j < 10; j++) vlo[j] = movm(vlo[j]);
  const bool far0 = 2 * t > g, far1 = 2 * t + 1 > g;
  const uint32_t mfar = (far0 ? 0x0000FFFFu : 0u) | (far1 ? 0xFFFF0000u : 0u);
  float slo[4][2], lg[2][2];
  uint32_t phi[4], plo[4], qml[4], qmh[4];
#pragma unroll
  for (int h = 0; h < 4; h++) {
    const int f = h == 0 ? 0 : h == 1 ? 3 : h == 2 ? 5 : 8, hf = h < 2 ? 2 : 7;
    const bool mine = (h & 1) ? t >= 2 : t < 2;
    qml[h] = mine ? qlo[hf] : 0u;
    qmh[h] = mine ? qhi[hf] : 0u;
    float a[4] = {0.f, 0.f, 0.f, 0.f}, c[4] = {0.f, 0.f, 0.f, 0.f};
    mma16816(a, qlo[f], qhi[f], qlo[f + 1], qhi[f + 1], klo[f], klo[f + 1]);
    mma16816(c, qlo[f], qhi[f], qlo[f + 1], qhi[f + 1], khi[f], khi[f + 1]);
    mma1688(a, qml[h], qmh[h], klo[hf]);
    mma1688(c, qml[h], qmh[h], khi[hf]);
    slo[h][0] = a[0];
    slo[h][1] = a[1];
    lg[h & 1][0] = far0 ? a[2] : c[2];
    lg[h & 1][1] = far1 ? a[3] : c[3];
    if (h & 1) softmax_two(lg, phi[h - 1], phi[h]);
  }
  TSIF(par == 0 && w == 1, 65);
  wg_sync(1 + par);
  TSIF(par == 0 && w == 1, 66);
  const bool nohist = (w == 0) && (b < 8);
  const uint4* hp = g_halo + ((b - 8) * 2 + par) * 224 + lane;
  uint32_t tg[7];
  if (w > 0) {
    const uint4 v0 = lds128(xa + (w - 1) * 2560), v1 = lds128(xa + (w - 1) * 2560 + 512), v2 = lds128(xa + (w - 1) * 2560 + 1024);
    const uint4 v3 = lds128(xa + (w - 1) * 2560 + 1536), v4 = lds128(xa + (w - 1) * 2560 + 2048);
    kpv[0] = v0.x; kpv[1] = v0.y; kpv[2] = v0.z; kpv[3] = v0.w; kpv[4] = v1.x; kpv[5] = v1.y; kpv[6] = v1.z; kpv[7] = v1.w;
    kpv[8] = v2.x; kpv[9] = v2.y; vpv[0] = v2.z; vpv[1] = v2.w; vpv[2] = v3.x; vpv[3] = v3.y; vpv[4] = v3.z; vpv[5] = v3.w;
    vpv[6] = v4.x; vpv[7] = v4.y; vpv[8] = v4.z; vpv[9] = v4.w;
  } else if (nohist) {
#pragma unroll
    for (int j = 0; j < 10; j++) kpv[j] = vpv[j] = 0u;
  } else {
    TSIF(par == 0, 77);
    halo_read(kpv, vpv, tg, hp);
  }
  if (w == 0 && !nohist) {
    int spins = 0;
    while (true) {
      bool ok = true;
#pragma unroll
      for (int j = 0; j < 7; j++) ok = ok && tg[j] == tag;
      if (__all_sync(0xffffffffu, ok) || ++spins > SPIN_LIMIT) break;
      halo_read(kpv, vpv, tg, hp);
    }
    TSIF(par == 0, 79);
  }
#pragma unroll
  for (int h = 0; h < 4; h++) {
    const int f = h == 0 ? 0 : h == 1 ? 3 : h == 2 ? 5 : 8, hf = h < 2 ? 2 : 7;
    float a[4] = {0.f, 0.f, 0.f, 0.f};
    mma16816(a, qlo[f], qhi[f], qlo[f + 1], qhi[f + 1], kpv[f], kpv[f + 1]);
    mma1688(a, qml[h], qmh[h], kpv[hf]);
    const float ninf = __int_as_float(0xff800000);
    lg[h & 1][0] = far0 ? (nohist ? ninf : a[0]) : slo[h][0];
    lg[h & 1][1] = far1 ? (nohist ? ninf : a[1]) : slo[h][1];
    if (h & 1) softmax_two(lg, plo[h - 1], plo[h]);
  }
  TSIF(par == 0 && w <= 1, 67 + w);
  uint32_t ov[20];
#pragma unroll
  for (int hp = 0; hp < 2; hp++) {
    const int hf = hp ? 7 : 2;
    float sh[4] = {0.f, 0.f, 0.f, 0.f}, i0 = 0.f, i1 = 0.f;
#pragma unroll
    for (int e = 0; e < 2; e++) {
      const int h = 2 * hp + e, f = h == 0 ? 0 : h == 1 ? 3 : h == 2 ? 5 : 8;
      const uint32_t a0 = plo[h] & mfar, a2 = plo[h] & ~mfar, a3 = phi[h] & mfar, c1 = phi[h] & ~mfar;
      float sum[4] = {0.f, 0.f, 0.f, 0.f};
      mma1688(sum, plo[h], phi[h], 0x3F803F80u);
      const float r0 = rcp(sum[0]), r1 = rcp(sum[2]);
#pragma unroll
      for (int j = f; j < f + 2; j++) {
        float o[4] = {0.f, 0.f, 0.f, 0.f};
        mma16816(o, a0, 0u, a2, a3, vpv[j], vlo[j]);
        mma1688(o, 0u, c1, vhi[j]);
        ov[2 * j] = pack2(o[0] * r0, o[1] * r0);
        ov[2 * j + 1] = pack2(o[2] * r1, o[3] * r1);
      }
      const bool mine = e ? g >= 4 : g < 4;
      mma16816(sh, a0, 0u, a2, a3, mine ? vpv[hf] : 0u, mine ? vlo[hf] : 0u);
      mma1688(sh, 0u, c1, mine ? vhi[hf] : 0u);
      if (e == 0 || t >= 2) {
        i0 = r0;
        i1 = r1;
      }
    }
    ov[2 * hf] = pack2(sh[0] * i0, sh[1] * i0);
    ov[2 * hf + 1] = pack2(sh[2] * i1, sh[3] * i1);
  }
  TS(32 + 4 * par + w);
  mbar_wait(sb + OFF_BAR + 8 * B_P1, 0);
  const uint32_t oa = sb + OFF_OA + (lane >> 4) * 2048 + (32 * w + 2 * (lane & 15) + par) * 16;
#pragma unroll
  for (int j = 0; j < 5; j++) stsm4(oa + 4096 * j, ov + 4 * j);
  TSIF(par == 0 && w == 0, 120);
  fence_async_smem();
  TSIF(par == 0 && w == 0, 121);
  __syncwarp();
  if (lane == 0) mbar_arrive(sb + OFF_BAR + 8 * B_ATTN);
  TSM(w == 0 || w == 2, 122 + par + (w == 2 ? 3 : 0));
}

struct Maps {
  CUtensorMap x, wm, wt, k, v, y, wo, qm, qt, om, ot, yl, ol;
};

__device__ __forceinline__ void load_stage(uint32_t sb, int kb, int b, const Maps& m) {
  const uint32_t st = sb + (kb & 3) * STAGE_BYTES, bar = sb + OFF_BAR + 8 * (B_FULL1 + (kb & 3));
  const int r = b >> 3, hg = b & 7, slab = kb - KV_KB;
  const bool kv = slab >= 0 && slab < 5;
  const uint32_t kbar = sb + OFF_BAR + 8 * (B_KV + slab), dst = sb + OFF_KVS + slab * KVS_BYTES;
  mbar_expect_tx(bar, STAGE_BYTES);
  if (kv) mbar_expect_tx(kbar, KVS_BYTES);
  tma_3d(st, &m.x, 64 * kb, 64 * r, 0, bar);
  tma_3d(st + ST_W, &m.wm, 80 * hg + (tail_first(hg) ? 16 : 0), 64 * kb, 0, bar);
  tma_3d(st + ST_WT, &m.wt, 80 * hg + (tail_first(hg) ? 0 : 64), 64 * kb, 0, bar);
  if (kv) tma_3d(dst, &m.k, 0, 32 * (b >> 1) - 3, 2 * slab + (b & 1), kbar);
  if (kv) tma_3d(dst + KVS_V, &m.v, 0, 32 * (b >> 1), 2 * slab + (b & 1), kbar);
}

__global__ void __launch_bounds__(NTHR, 1) fused_kernel(const __grid_constant__ Maps m, const Params p) {
  extern __shared__ __align__(1024) uint8_t smem[];
  const uint32_t sb = (uint32_t)__cvta_generic_to_shared(smem);
  const uint32_t bars = sb + OFF_BAR;
  const int tid = threadIdx.x, lane = tid & 31;
  int b = blockIdx.x;
  b = (((b & 63) >> 3) * 2 + (b & 1)) * 8 + (((b < 64 ? 0x6521 : 0x7430) >> (4 * ((b >> 1) & 3))) & 7);
  const int r = b >> 3, hg = b & 7;

  if (tid == T_ISSUE) {
    TSM(true, 0);
    mbar_init(bars + 8 * B_F0, 1);
    fence_async_smem();
    mbar_expect_tx(bars + 8 * B_F0, ST_WT);
    tma_3d(sb, &m.x, 0, 64 * r, 0, bars + 8 * B_F0);
    tma_3d(sb + ST_W, &m.wm, 80 * hg + (tail_first(hg) ? 16 : 0), 0, 0, bars + 8 * B_F0);
#pragma unroll
    for (int i = 0; i < 4; i++) mbar_init(bars + 8 * (B_FULL1 + i), 1);
    fence_async_smem();
    mbar_expect_tx(bars + 8 * B_FULL1, STAGE_BYTES - ST_WT);
    tma_3d(sb + ST_WT, &m.wt, 80 * hg + (tail_first(hg) ? 0 : 64), 0, 0, bars + 8 * B_FULL1);
    load_stage(sb, 1, b, m);
  } else if (tid == T_INIT) {
#pragma unroll
    for (int i = 0; i < B_F0; i++) mbar_init(bars + 8 * i, i < B_GATE ? 8 : i < B_CVD ? 4 : i == B_CVD ? 20 : 1);
    fence_async_smem();
  }
  const int warp = __shfl_sync(0xffffffffu, tid >> 5, 0), wg = warp >> 2, w = warp & 3;
  __syncthreads();

  if (wg == 3) {
    asm volatile("setmaxnreg.dec.sync.aligned.u32 56;");
    if (w == 0) {
      if (lane == 0) {
#pragma unroll 1
        for (int kb = 2; kb < 10; kb++) {
          if (kb >= 4) mbar_wait(bars + 8 * (kb == 7 ? B_E3 : B_EMPTY1 + (kb & 3)), (kb >> 3) & 1);
          TSIF(kb >= 4, 44 + kb);
          load_stage(sb, kb, b, m);
          TSIF(kb == 3, 60);
          if (kb == TRIG_KB) mbar_arrive(bars + 8 * B_LAST);
        }
        mbar_wait(bars + 8 * B_WOP, 0);
        mbar_wait(bars + 8 * WL_TRIG, 0);
        mbar_wait(bars + 8 * B_EPOCH, 0);
        flag_wait(g_cnt + C_W + 32 * hg, (lds32(sb + OFF_EPOCH) + 1) * 16);
        TS(30);
#pragma unroll 1
        for (int j = 0; j < 8; j++) {
          if (j >= 6) mbar_wait(bars + 8 * (B_EMPTY2 + j - 6), 0);
          if (j == 4) mbar_wait(bars + 8 * (RB32 & 2 ? B_ORB : B_ATTN), 0);
          TSIF(j >= 6, 100 + j);
          mbar_expect_tx(bars + 8 * (B_FULL2 + j), j == 0 ? WO_BYTES : j == 5 ? O_BYTES + WO_BYTES + 512 : O_BYTES + WO_BYTES);
          bulk_load(sb + off_w(j), g_WO + (hg * 8 + step_src(hg, j)) * 800, WO_BYTES, bars + 8 * (B_FULL2 + j));
        }
        mbar_wait(bars + 8 * (B_EMPTY2 + 3), 0);
        mbar_expect_tx(bars + 8 * B_QF, O_BYTES);
        tma_2d(sb + OFF_QS, &m.qm, 80 * hg, 128 * r, bars + 8 * B_QF);
        tma_2d(sb + OFF_QT, &m.qt, 80 * hg + 64, 128 * r, bars + 8 * B_QF);
      }
    } else if (w == 1) {
      unsigned epoch = 0;
      if (lane == 0) {
        epoch = atomicAdd(g_cnt + C_LAUNCH, 1u) / NCTA;
        asm volatile("st.shared.u32 [%0], %1;" ::"r"(sb + OFF_EPOCH), "r"(epoch) : "memory");
        mbar_arrive(bars + 8 * B_EPOCH);
        mbar_wait(bars + 8 * B_KVD, 0);
        mbar_expect_tx(bars + 8 * B_HB, 5 * 4096);
#pragma unroll 1
        for (int c = 0; c < 5; c++) {
          if (c == 3) mbar_wait(bars + 8 * B_S3, 0);
          bulk_load(sb + off_ch(c) + U_BYTES, p.ssm_k + (5 * b + c) * SEQ, 4096, bars + 8 * B_HB);
        }
#pragma unroll
        for (int c = 0; c < 4; c++) mbar_expect_tx(bars + 8 * (B_U + c), c < 3 ? U_BYTES : 2 * U_BYTES);
        const uint4* usrc = g_U + 5 * b * U_PITCH;
        mbar_wait(bars + 8 * B_USIG, 0);
        flag_wait(g_cnt + C_PREP + 32 * (b & 15), (epoch + 1) * NCTA);
        TS(23);
#pragma unroll
        for (int c = 0; c < 5; c++) {
          if (c == 3) mbar_wait(bars + 8 * (B_U + 2), 0);
          bulk_load(sb + off_ch(c), usrc + c * U_PITCH, U_BYTES, bars + 8 * (B_U + (c < 3 ? c : 3)));
          TSIF(c == 0 || c == 4, 116 + (c >> 2));
        }
      }
      epoch = __shfl_sync(0xffffffffu, epoch, 0);
      if (lane < 8) {
        const int src = (b & ~7) | step_src(hg, lane);
        mbar_wait(bars + 8 * B_ATTN, 0);
        TS(20);
        bool seen = false;
#pragma unroll 1
        for (int spins = 0; spins < SPIN_LIMIT; spins++) {
          const bool now = !seen && (int)(flag_read(g_cnt + C_O + 32 * src) - (epoch + 1)) >= 0;
          if (now && lane >= 1 && lane < 4) bulk_load(sb + off_o(lane), g_O + src * 1280, O_BYTES, bars + 8 * (B_FULL2 + lane));
          seen = seen || now;
          if (__all_sync(0xff, seen)) break;
        }
        TS(21);
        if (lane == 5) bulk_load(sb + OFF_GATE, g_gate + 128 * r, 512, bars + 8 * (B_FULL2 + 5));
#pragma unroll 1
        for (int j = 4; j < 8; j++) {
          if (lane == j) {
            mbar_wait(bars + 8 * (j < 6 ? B_C34 : B_EMPTY2 + j - 6), 0);
            bulk_load(sb + off_o(j), g_O + src * 1280, O_BYTES, bars + 8 * (B_FULL2 + j));
          }
          __syncwarp(0xff);
        }
        TS(22);
      }
    } else if (w == 2) {
      mbar_wait(bars + 8 * B_PREP, 0);
      flag_signal(g_cnt + C_PREP, 16, lane);
      TS(25);
      if (lane == 0) {
        mbar_arrive(bars + 8 * B_USIG);
        mbar_expect_tx(bars + 8 * B_ORB, (RB32 & 2 ? O_BYTES / 4 : O_BYTES) + 64);
        mbar_wait(bars + 8 * B_GATE, 0);
        publish(g_gate + 16 * b, sb + OFF_GATE + 64 * hg, 64, bars + 8 * B_ORB);
        mbar_wait(bars + 8 * B_ATTN, 0);
        if (RB32 & 2) {
          bulk_store(g_O + b * 1280, sb + OFF_OA, O_BYTES);
          bulk_wait_read();
          tma_2d(sb + OFF_KVX + 10240, &m.ol, 48, b * 160, bars + 8 * B_ORB);
        } else {
          publish(g_O + b * 1280, sb + OFF_OA, O_BYTES, bars + 8 * B_ORB);
        }
        TS(74);
        mbar_wait(bars + 8 * B_ORB, 0);
        flag_bump(g_cnt + C_O + 32 * b);
        TS(26);
        mbar_arrive(bars + 8 * B_OSIG);
      }
    } else {
      if (lane == 0) {
        uint4* dst = g_WO + (hg * 8 + (r >> 1)) * 800 + (r & 1) * 80;
        mbar_wait(bars + 8 * B_S3, 0);
        asm volatile("cp.async.bulk.prefetch.L2.global [%0], 6400;" ::"l"(p.wo + b * 3200) : "memory");
        mbar_wait(bars + 8 * B_P1, 0);
        mbar_wait(bars + 8 * WB_TRIG, 0);
        mbar_expect_tx(bars + 8 * B_WST, WO_BYTES / 2);
        tma_3d(sb + OFF_WA, &m.wo, 0, 40 * r, 5 * hg, bars + 8 * B_WST);
        mbar_wait(bars + 8 * B_WST, 0);
#pragma unroll 1
        for (int n = 0; n < 5; n++) bulk_store(dst + 160 * n, sb + OFF_WA + 1280 * n, 1280);
        bulk_wait_read();
        mbar_expect_tx(bars + 8 * B_WST, WO_BYTES / 2);
#pragma unroll 1
        for (int n = 0; n < 5; n++) bulk_load(sb + OFF_WA + 1280 * n, dst + 160 * n, 1280, bars + 8 * B_WST);
        mbar_wait(bars + 8 * B_WST, 1);
        flag_bump(g_cnt + C_W + 32 * hg);
        mbar_arrive(bars + 8 * B_WOP);
        TS(71);
        mbar_expect_tx(bars + 8 * B_C34, 3 * (RB32 & 1 ? 1024 : U_BYTES));
        mbar_expect_tx(bars + 8 * B_YRB, 2 * (RB32 & 1 ? 1024 : U_BYTES));
#pragma unroll 1
        for (int c = 0; c < 5; c++) {
          mbar_wait(bars + 8 * (B_YST + c), 0);
          if (RB32 & 1) {
            bulk_store(g_U + (5 * b + c) * U_PITCH, sb + off_ch(c), U_BYTES);
            bulk_wait_read();
            tma_2d(sb + off_ch(c), &m.yl, 48, (5 * b + c) * (U_PITCH / 8), bars + 8 * (c < 3 ? B_C34 : B_YRB));
          } else {
            publish(g_U + (5 * b + c) * U_PITCH, sb + off_ch(c), U_BYTES, bars + 8 * (c < 3 ? B_C34 : B_YRB));
          }
        }
        TS(75);
        mbar_wait(bars + 8 * B_C34, 0);
        mbar_wait(bars + 8 * B_YRB, 0);
        flag_bump(g_cnt + C_Y + 32 * (b >> 4));
        TS(27);
        mbar_arrive(bars + 8 * B_YSIG);
        mbar_expect_tx(bars + 8 * B_YFULL, 20480);
        flag_wait(g_cnt + C_Y + 32 * hg, (lds32(sb + OFF_EPOCH) + 1) * 16);
        TS(24);
        tma_2d(sb + OFF_YT, &m.y, 128 * r, 80 * hg, bars + 8 * B_YFULL);
        tma_2d(sb + OFF_YT + 10240, &m.y, 128 * r + 64, 80 * hg, bars + 8 * B_YFULL);
      }
    }
  } else {
    asm volatile("setmaxnreg.inc.sync.aligned.u32 152;");
    if (wg < 2) {
      float acc[120];
#pragma unroll
      for (int i = 0; i < 120; i++) acc[i] = 0.f;
      const uint32_t da = desc_lo(sb + wg * 8192, 16), db = desc_lo(sb + ST_W, 8192), dc = desc_lo(sb + ST_WT, 2048);
      mbar_wait(bars + 8 * B_F0, 0);
      TSIF(w == 0 && wg == 0, 1);
      wg_fence();
#pragma unroll
      for (int k = 0; k < 4; k++) WgSST<192>::mma<HI_SW128, HI_SW128>(acc, da + 2 * k, db + 128 * k, 1);
      wg_commit();
      mbar_wait(bars + 8 * B_FULL1, 0);
      wg_fence();
#pragma unroll
      for (int k = 0; k < 4; k++) WgSST<48>::mma<HI_SW128, HI_SW32>(acc + 96, da + 2 * k, dc + 32 * k, 1);
      wg_commit();
#pragma unroll 1
      for (int kb = 1; kb < 10; kb++) {
        mbar_wait(bars + 8 * (B_FULL1 + (kb & 3)), (kb >> 2) & 1);
        const uint32_t so = (kb & 3) * (STAGE_BYTES >> 4);
        wg_fence();
#pragma unroll
        for (int k = 0; k < 4; k++) {
          WgSST<192>::mma<HI_SW128, HI_SW128>(acc, da + so + 2 * k, db + so + 128 * k, 1);
          WgSST<48>::mma<HI_SW128, HI_SW32>(acc + 96, da + so + 2 * k, dc + so + 32 * k, 1);
        }
        wg_commit();
        wg_wait<1>();
        if (lane == 0) mbar_arrive(bars + 8 * (kb == 4 ? B_E3 : B_EMPTY1 + ((kb - 1) & 3)));
      }
      mbar_wait(bars + 8 * B_EPOCH, 0);
      const uint32_t tag = lds32(sb + OFF_EPOCH) + 1;
      mbar_wait(bars + 8 * B_S3, 0);
      wg_wait<0>();
      pin<120>(acc);
      if (lane == 0) mbar_arrive(bars + 8 * B_P1);
      TSM(w == 0, 3 + wg);
      attention(acc, sb, b, wg, w, lane, tag);
    } else {
      const int tw = tid & 127, chl = 64 * (b & 1) + 8 * w + (lane >> 2);
      uint4* up = g_U + chl * U_PITCH + ((4 * (b >> 1) + (lane & 3)) ^ ((b >> 2) & 1));
      uint2 sw[10];
      uint32_t dv = 0;
      if (lane < 5) dv = __ldg(reinterpret_cast<const unsigned short*>(p.ssm_D) + 5 * b + lane);
#pragma unroll
      for (int i = 0; i < 10; i++) sw[i] = ldg64(reinterpret_cast<const uint2*>(p.shift_k) + chl + 128 * (i >> 1) + 32 * (i & 1));
      uint32_t tab[12];
      uint32_t tt[2];
      fft_tables(tab, tw);
      fft_twiddles(tt, tw);
      uint4 res[10];
#pragma unroll
      for (int i = 0; i < 10; i++) res[i] = make_uint4(0, 0, 0, 0);
#pragma unroll 1
      for (int slab = 0; slab < 5; slab++) {
#pragma unroll
        for (int i = 0; i < 8; i++) res[i] = res[i + 2];
        prep_slab(res + 8, sw, sb, slab, w, lane);
        TSIF(w == 0, 99 + 4 * slab);
#pragma unroll
        for (int i = 0; i < 8; i++) sw[i] = sw[i + 2];
      }
      TSIF(w == 0, 28);
      __syncwarp();
      if (lane == 0) mbar_arrive(bars + 8 * B_KVD + ((res[8].x ^ res[9].x) & p.zero));
      mbar_wait(bars + 8 * B_KVD, 0);
      fft_tables_store(tab, sb, tw);
      mbar_wait(bars + 8 * B_LAST, 0);
#pragma unroll
      for (int i = 0; i < 10; i++) up[(128 * (i >> 1) + 32 * (i & 1)) * U_PITCH] = res[i];
      __syncwarp();
      if (lane == 0) mbar_arrive(bars + 8 * B_PREP);
      TSIF(w == 0, 5);
      mbar_wait(bars + 8 * B_LAST, 0);
      prep_gate(p, sb, b, w, lane);
      __syncwarp();
      if (lane == 0) mbar_arrive(bars + 8 * B_GATE);
      TSIF(w == 0, 72);
      mbar_wait(bars + 8 * B_HB, 0);
      TSIF(w == 0, 2);
      const uint32_t ha = sb + U_BYTES + ((tw >> 3) * 16 + 8 + (tw & 7)) * 16;
      uint4 hv[5];
#pragma unroll
      for (int c = 0; c < 5; c++) hv[c] = lds128(ha + off_ch(c));
      __syncwarp();
#pragma unroll
      for (int c = 0; c < 5; c++) sts128((ha ^ 16) + off_ch(c), hv[c].x, hv[c].y, hv[c].z, hv[c].w);
      asm volatile("st.shared.v2.u32 [%0], {%1, %2};" ::"r"(sb + OFF_TT + 8 * tw), "r"(tt[0]), "r"(tt[1]) : "memory");
      if (tw < 5) asm volatile("st.shared.f32 [%0], %1;" ::"r"(sb + OFF_D + 4 * tw), "f"(bf_lo(dv) * 0.125f) : "memory");
      fence_async_smem();
      __syncwarp();
      if (lane == 0) mbar_arrive(bars + 8 * B_HA);
      TSIF(w == 0, 6);
    }

    FftConst fc;
    TSM(w == 0 && wg == 0, 104);
    mbar_wait(bars + 8 * B_HA, 0);
    fft_matrices(fc, sb, w, lane);
    TSM(w == 0 && wg == 0, 105);
    TSM(w == 0 && wg == 2, 124);
#pragma unroll 1
    for (uint32_t tasks = wg == 0 ? TASK0 : wg == 1 ? TASK1 : TASK2; tasks; tasks >>= 4) {
      const int c = (tasks & 7) - 1;
      conv_channel(fc, sb, c, wg, w, lane);
      if (lane == 0) mbar_arrive(bars + 8 * (B_YST + c));
      TSM(w == 0, 10 + c);
    }

    if (wg != WO_SKIP) {
      const int wg = (warp >> 2) > WO_SKIP ? (warp >> 2) - 1 : warp >> 2;
      const int g = lane >> 2;
      float acc[40];
#pragma unroll
      for (int i = 0; i < 40; i++) acc[i] = 0.f;
      const uint32_t da = desc_lo(sb + wg * 1024, 2048), db = desc_lo(sb, 2560);
      mbar_wait(bars + 8 * B_ORB, 0);
      mbar_wait(bars + 8 * B_FULL2, 0);
      TSM(w == 0, 15 + wg);
#pragma unroll 1
      for (int j = 0; j < 8; j++) {
        if (j == (wg ? WO_E1 : WO_E0)) mbar_wait(bars + 8 * B_CVD, 0);
        mbar_wait(bars + 8 * (B_FULL2 + j), 0);
        TSM(w == 0 && wg == 0, 44 + (j < 4 ? j : j + 6));
        const uint32_t oa = da + (off_o(j) >> 4), ob = db + (off_w(j) >> 4);
        wg_fence();
#pragma unroll
        for (int k = 0; k < 5; k++) WgSST<80>::mma<HI_NONE, HI_SW32>(acc, oa + 256 * k, ob + 32 * k, 1);
        wg_commit();
        wg_wait<1>();
        if (j >= 1 && j <= 4 && lane == 0) mbar_arrive(bars + 8 * (B_EMPTY2 + j - 1));
      }
      TSIF(w == 0 && wg == 0, 113);
      const int tr = 64 * wg + 16 * w + (lane & 15);
      const uint32_t fm = sb + OFF_QS + tr * 128, fx = (lane >> 4) ^ (tr & 7);
      const uint32_t ft = sb + OFF_QT + tr * 32 + (((lane >> 4) ^ (tr >> 2)) & 1) * 16;
      const float g0 = __uint_as_float(lds32(sb + OFF_GATE + (64 * wg + 16 * w + g) * 4));
      const float g1 = __uint_as_float(lds32(sb + OFF_GATE + (64 * wg + 16 * w + 8 + g) * 4));
      const uint32_t ga = pack2(g0, g0), gb = pack2(g1, g1);
      const uint32_t na = pack2(1.f - g0, 1.f - g0), nb = pack2(1.f - g1, 1.f - g1);

      uint32_t qf[20];
      mbar_wait(bars + 8 * B_QF, 0);
      TSM(w == 0 && wg == 0, 99);
#pragma unroll
      for (int j = 0; j < 5; j++) ldsm4(qf + 4 * j, j < 4 ? fm + ((fx ^ (2 * j)) << 4) : ft);
#pragma unroll
      for (int i = 0; i < 20; i++) {
        qf[i] = bmul((i & 1) ? gb : ga, qf[i]);
        asm volatile("" : "+r"(qf[i]));
      }

      wg_wait<0>();
      pin<40>(acc);
      TSM(w == 0, 17 + wg);
      uint32_t pb[20];
#pragma unroll
      for (int j = 0; j < 10; j++) {
        pb[2 * j] = bmul(na, pack2(acc[4 * j], acc[4 * j + 1]));
        pb[2 * j + 1] = bmul(nb, pack2(acc[4 * j + 2], acc[4 * j + 3]));
        asm volatile("" : "+r"(pb[2 * j]), "+r"(pb[2 * j + 1]));
      }
      const uint32_t ya = sb + OFF_YT + wg * 10240 + ((lane >> 4) * 8 + (lane & 7)) * 128 +
                          (((2 * w + (((lane >> 3) & 1) ^ wg)) ^ (lane & 7)) << 4);
      mbar_wait(bars + 8 * B_YFULL, 0);
      TSM(w == 0 && wg == 0, 19);
#pragma unroll
      for (int j = 0; j < 5; j++) {
        uint32_t y[4];
        ldsm4t(y, ya + 2048 * j);
#pragma unroll
        for (int i = 0; i < 4; i++)
          qf[4 * j + i] = bfma(qf[4 * j + i], y[i], pb[4 * j + i]);
      }
#pragma unroll
      for (int j = 0; j < 5; j++) stsm4(j < 4 ? fm + ((fx ^ (2 * j)) << 4) : ft, qf + 4 * j);
      fence_async_smem();
      __syncwarp();
      if (lane == 0) {
        const int row = 64 * wg + 16 * w;
        asm volatile("cp.async.bulk.tensor.2d.global.shared::cta.bulk_group [%0, {%2, %3}], [%1];"
                     ::"l"(&m.om), "r"(sb + OFF_QS + row * 128), "r"(80 * hg), "r"(128 * r + row) : "memory");
        asm volatile("cp.async.bulk.tensor.2d.global.shared::cta.bulk_group [%0, {%2, %3}], [%1];"
                     ::"l"(&m.ot), "r"(sb + OFF_QT + row * 32), "r"(80 * hg + 64), "r"(128 * r + row) : "memory");
        asm volatile("cp.async.bulk.commit_group;\ncp.async.bulk.wait_group.read 0;" ::: "memory");
      }
      TSM(w == 0 || w == 3, 40 + 2 * wg + (w & 1));
    }
  }
}

typedef CUresult (*EncodeFn)(CUtensorMap*, CUtensorMapDataType, cuuint32_t, void*, const cuuint64_t*, const cuuint64_t*,
                             const cuuint32_t*, const cuuint32_t*, CUtensorMapInterleave, CUtensorMapSwizzle,
                             CUtensorMapL2promotion, CUtensorMapFloatOOBfill);

void encode(EncodeFn fn, CUtensorMap* tm, const void* base, int rank, const cuuint64_t* dims, const cuuint64_t* strides,
            const cuuint32_t* box, CUtensorMapSwizzle swz) {
  const cuuint32_t ones[3] = {1, 1, 1};
  fn(tm, CU_TENSOR_MAP_DATA_TYPE_BFLOAT16, rank, const_cast<void*>(base), dims, strides, box, ones,
     CU_TENSOR_MAP_INTERLEAVE_NONE, swz, CU_TENSOR_MAP_L2_PROMOTION_L2_128B, CU_TENSOR_MAP_FLOAT_OOB_FILL_NONE);
}

}

extern "C" void kernel_launch(void* const* d_in, const int* in_sizes, int n_in, void* d_out, int out_size) {
  (void)in_sizes; (void)n_in; (void)out_size;
  Params p;
  p.q = (const __nv_bfloat16*)d_in[0];
  p.k = (const __nv_bfloat16*)d_in[1];
  p.v = (const __nv_bfloat16*)d_in[2];
  p.shift_k = (const __nv_bfloat16*)d_in[3];
  p.ssm_k = (const __nv_bfloat16*)d_in[4];
  p.ssm_D = (const __nv_bfloat16*)d_in[5];
  p.wqkv = (const __nv_bfloat16*)d_in[7];
  p.wo = (const __nv_bfloat16*)d_in[8];
  p.gate_w = (const __nv_bfloat16*)d_in[9];
  p.out = (__nv_bfloat16*)d_out;
  p.zero = 0;

  static EncodeFn fn = nullptr;
  static void *yaddr = nullptr, *oaddr = nullptr;
  if (!fn) {
    cudaDriverEntryPointQueryResult qr;
    void* f = nullptr;
    cudaGetDriverEntryPoint("cuTensorMapEncodeTiled", &f, cudaEnableDefault, &qr);
    fn = (EncodeFn)f;
    cudaGetSymbolAddress(&yaddr, g_U);
    cudaGetSymbolAddress(&oaddr, g_O);
    cudaFuncSetAttribute(fused_kernel, cudaFuncAttributeMaxDynamicSharedMemorySize, SMEM_BYTES);
  }
  Maps m;
  {
    const cuuint64_t dims[3] = {640, 1024, 2}, st[2] = {2560, 1280};
    const cuuint32_t box[3] = {64, 64, 2};
    encode(fn, &m.x, p.q, 3, dims, st, box, CU_TENSOR_MAP_SWIZZLE_128B);
  }
  {
    const cuuint64_t dims[3] = {640, 640, 3}, st[2] = {3840, 1280};
    const cuuint32_t box[3] = {64, 64, 3}, boxt[3] = {16, 64, 3};
    encode(fn, &m.wm, p.wqkv, 3, dims, st, box, CU_TENSOR_MAP_SWIZZLE_128B);
    encode(fn, &m.wt, p.wqkv, 3, dims, st, boxt, CU_TENSOR_MAP_SWIZZLE_32B);
  }
  {
    const cuuint64_t dims[3] = {64, 2048, 10}, st[2] = {1280, 128};
    const cuuint32_t boxk[3] = {64, 35, 1}, boxv[3] = {64, 32, 1};
    encode(fn, &m.k, p.k, 3, dims, st, boxk, CU_TENSOR_MAP_SWIZZLE_128B);
    encode(fn, &m.v, p.v, 3, dims, st, boxv, CU_TENSOR_MAP_SWIZZLE_128B);
  }
  {
    const cuuint64_t dims[3] = {16, 640, 40}, st[2] = {1280, 32};
    const cuuint32_t box[3] = {16, 40, 5};
    encode(fn, &m.wo, p.wo, 3, dims, st, box, CU_TENSOR_MAP_SWIZZLE_32B);
  }
  {
    const cuuint64_t dims[2] = {2048, 640}, st[1] = {U_PITCH * 16};
    const cuuint32_t box[2] = {64, 80};
    encode(fn, &m.y, yaddr, 2, dims, st, box, CU_TENSOR_MAP_SWIZZLE_128B);
    const cuuint64_t dl[2] = {64, DIM * U_PITCH / 8}, dol[2] = {64, NCTA * 160}, sl[1] = {128};
    const cuuint32_t bl[2] = {16, 32}, bol[2] = {16, 160};
    encode(fn, &m.yl, yaddr, 2, dl, sl, bl, CU_TENSOR_MAP_SWIZZLE_NONE);
    encode(fn, &m.ol, oaddr, 2, dol, sl, bol, CU_TENSOR_MAP_SWIZZLE_NONE);
  }
  {
    const cuuint64_t dims[2] = {640, 2048}, st[1] = {1280};
    const cuuint32_t bqm[2] = {64, 128}, bqt[2] = {16, 128}, bom[2] = {64, 16}, bot[2] = {16, 16};
    encode(fn, &m.qm, p.q, 2, dims, st, bqm, CU_TENSOR_MAP_SWIZZLE_128B);
    encode(fn, &m.qt, p.q, 2, dims, st, bqt, CU_TENSOR_MAP_SWIZZLE_32B);
    encode(fn, &m.om, p.out, 2, dims, st, bom, CU_TENSOR_MAP_SWIZZLE_128B);
    encode(fn, &m.ot, p.out, 2, dims, st, bot, CU_TENSOR_MAP_SWIZZLE_32B);
  }
  fused_kernel<<<NCTA, NTHR, SMEM_BYTES>>>(m, p);
}
```

```cpp
#include <cuda.h>
#include <cuda_bf16.h>
#include <cuda_runtime.h>
#include <stdint.h>

namespace {

constexpr int SEQ = 2048, DIM = 640, NCTA = 128, NTHR = 512;

#define TRIG_KB 9
#define KV_KB 2
#define DEV_EXIT 0
#define FENCE_LO 0
#define FENCE_HI 0
#define WB_TRIG B_USIG
#define T_ISSUE 256
#define RB32 3
#define WO_SKIP 1
#define WO_E0 1
#define WO_E1 0
#define Y_SPLIT 1
#define W_LATE Y_SPLIT
#define T_INIT 448
#define TASK0 0x3
#define TASK1 0x52
#define TASK2 0x41
#define WL_TRIG B_WOP

constexpr uint32_t STAGE_BYTES = 47104, ST_W = 16384, ST_WT = 40960;
constexpr uint32_t O_BYTES = 20480, WO_BYTES = 12800;
constexpr uint32_t OFF_OA = 0;
constexpr uint32_t OFF_QS = 3 * O_BYTES, OFF_QT = OFF_QS + 16384;
constexpr uint32_t OFF_WC = 81920;
constexpr uint32_t OFF_WA = 94720;
constexpr uint32_t OFF_GATE = 145920;
constexpr uint32_t OFF_TT = 146432;
constexpr uint32_t OFF_KVX = 148480;
constexpr uint32_t OFF_CH3 = 163840;
constexpr uint32_t CH_BYTES = 12288, U_BYTES = 4096;
constexpr uint32_t OFF_FT = 225280, OFF_GT = 229376;
constexpr uint32_t OFF_CH0 = 188416;
constexpr uint32_t OFF_KVS = OFF_CH0, KVS_V = 4480, KVS_BYTES = 8576;
constexpr uint32_t OFF_YT = Y_SPLIT ? 2 * O_BYTES : 163840;
constexpr uint32_t OFF_BAR = 231936;
constexpr uint32_t SMEM_BYTES = OFF_BAR + 512;

enum : uint32_t {
  B_EMPTY1 = 0, B_S3 = 3, B_E3 = 4, B_EMPTY2 = 5, B_ATTN = 9, B_P1 = 10,
  B_GATE = 11, B_HA = 12, B_KVD = 13, B_PREP = 14, B_YST = 15,
  B_CVD = 20,
  B_FULL2 = 21, B_U = 29, B_KV = 33, B_HB = 38, B_C34 = 39, B_YRB = 40, B_YFULL = 41, B_EPOCH = 42, B_LAST = 43, B_OSIG = 44,
  B_WOP = 45, B_USIG = 46, B_WST = 47, B_QF = 48, B_ORB = 49, B_YSIG = 50,
  B_F0 = 51, B_FULL1 = 52
};
constexpr uint32_t OFF_EPOCH = OFF_BAR + 8 * 58, OFF_D = OFF_BAR + 8 * 60;
__device__ __forceinline__ uint32_t off_o(int j) { return j < 4 ? OFF_OA + j * O_BYTES : j < 6 ? OFF_CH0 + (j - 4) * O_BYTES : OFF_OA + (j - 6) * O_BYTES; }
__device__ __forceinline__ uint32_t off_w(int j) { return j < 4 ? OFF_WA + j * WO_BYTES : j == 4 ? OFF_KVX : j == 5 ? OFF_WC : (W_LATE ? OFF_KVX + WO_BYTES : OFF_WA) + (j - 6) * WO_BYTES; }
__device__ __forceinline__ int step_src(int hg, int j) { return j == 0 ? hg : j <= hg ? j - 1 : j; }
__device__ __forceinline__ bool tail_first(int hg) { return (hg & 3) == 3; }
__device__ __forceinline__ uint32_t off_ch(int c) { return (c < 3 ? OFF_CH0 : OFF_CH3 - 3 * CH_BYTES) + c * CH_BYTES; }

__device__ __forceinline__ int chan(int b, int c) { return !Y_SPLIT ? 5 * b + c : 80 * (b >> 4) + (c < 3 ? 3 * (b & 15) + c : 45 + 2 * (b & 15) + c); }

#define U_PITCH 264
__device__ __align__(1024) uint4 g_U[DIM * U_PITCH];
__device__ __align__(128) uint4 g_O[NCTA * 1280];
__device__ uint4 g_WO[64 * 800];
__device__ uint4 g_halo[NCTA * 2 * 7 * 32];
__device__ __align__(128) float g_gate[SEQ];
__device__ unsigned g_cnt[32 * (1 + 2 * 16 + 8 + NCTA)];
constexpr int C_LAUNCH = 0, C_PREP = 32, C_Y = 32 * 17, C_YE = 32 * 25, C_W = 32 * 33, C_O = 32 * 41;

#define TSM(cond, slot) do { } while (0)
#define TSIF(cond, slot) do { if (__LINE__ >= FENCE_LO && __LINE__ < FENCE_HI) sched_fence(); } while (0)
__device__ __forceinline__ void sched_fence() {
  asm volatile("{\n.reg .pred p;\n.reg .u32 c;\nmov.u32 c, %%clock;\nsetp.eq.u32 p, c, 0;\n@p st.shared.u32 [%0], c;\n}"
               ::"r"(1024 + OFF_EPOCH + 4) : "memory");
}
#define TS(slot) TSIF(true, slot)

struct Params {
  const __nv_bfloat16 *q, *k, *v, *shift_k, *ssm_k, *ssm_D, *wqkv, *wo, *gate_w;
  __nv_bfloat16* out;
  uint32_t zero;
};

constexpr int SPIN_LIMIT = 1 << 17;

__device__ __forceinline__ void mbar_init(uint32_t bar, uint32_t count) {
  asm volatile("mbarrier.init.shared::cta.b64 [%0], %1;" ::"r"(bar), "r"(count) : "memory");
}
__device__ __forceinline__ void mbar_expect_tx(uint32_t bar, uint32_t bytes) {
  asm volatile("mbarrier.arrive.expect_tx.shared::cta.b64 _, [%0], %1;" ::"r"(bar), "r"(bytes) : "memory");
}
__device__ __forceinline__ void mbar_arrive(uint32_t bar) {
  asm volatile("mbarrier.arrive.shared::cta.b64 _, [%0];" ::"r"(bar) : "memory");
}
__device__ __forceinline__ void mbar_wait(uint32_t bar, uint32_t parity) {
  uint32_t ok;
  int spins = 0;
  do {
      asm volatile("{\n.reg .pred p;\nmbarrier.try_wait.parity.shared::cta.b64 p, [%1], %2;\nselp.b32 %0, 1, 0, p;\n}"
                   : "=r"(ok) : "r"(bar), "r"(parity) : "memory");
    if (++spins > SPIN_LIMIT) break;
  } while (!ok);
}
__device__ __forceinline__ unsigned flag_read(const unsigned* p) {
  unsigned v;
  asm volatile("ld.relaxed.gpu.global.u32 %0, [%1];" : "=r"(v) : "l"(p) : "memory");
  return v;
}
__device__ __forceinline__ void flag_poll(const unsigned* p, unsigned target) {
  unsigned v;
  int spins = 0;
  do {
    asm volatile("ld.relaxed.gpu.global.u32 %0, [%1];" : "=r"(v) : "l"(p) : "memory");
    if (++spins > SPIN_LIMIT) break;
  } while ((int)(v - target) < 0);
}
__device__ __forceinline__ void flag_wait(const unsigned* p, unsigned target) {
  flag_poll(p, target);
}
__device__ __forceinline__ void flag_signal(unsigned* p, int n, int lane) {
  if (lane == 0) asm volatile("fence.release.gpu;" ::: "memory");
  __syncwarp();
  if (lane < n) asm volatile("red.relaxed.gpu.global.add.u32 [%0], 1;" ::"l"(p + 32 * lane) : "memory");
}
__device__ __forceinline__ void flag_bump(unsigned* p) {
  asm volatile("red.relaxed.gpu.global.add.u32 [%0], 1;" ::"l"(p) : "memory");
}
__device__ __forceinline__ void fence_async_smem() { asm volatile("fence.proxy.async.shared::cta;" ::: "memory"); }
__device__ __forceinline__ void wg_sync(int id) { asm volatile("bar.sync %0, 128;" ::"r"(id) : "memory"); }

__device__ __forceinline__ void tma_2d(uint32_t dst, const CUtensorMap* tm, int c0, int c1, uint32_t bar) {
  asm volatile("cp.async.bulk.tensor.2d.shared::cluster.global.mbarrier::complete_tx::bytes [%0], [%1, {%3, %4}], [%2];"
               ::"r"(dst), "l"(tm), "r"(bar), "r"(c0), "r"(c1) : "memory");
}
__device__ __forceinline__ void tma_3d(uint32_t dst, const CUtensorMap* tm, int c0, int c1, int c2, uint32_t bar) {
  asm volatile("cp.async.bulk.tensor.3d.shared::cluster.global.mbarrier::complete_tx::bytes [%0], [%1, {%3, %4, %5}], [%2];"
               ::"r"(dst), "l"(tm), "r"(bar), "r"(c0), "r"(c1), "r"(c2) : "memory");
}
__device__ __forceinline__ void bulk_load(uint32_t dst, const void* src, uint32_t bytes, uint32_t bar) {
  asm volatile("cp.async.bulk.shared::cluster.global.mbarrier::complete_tx::bytes [%0], [%1], %2, [%3];"
               ::"r"(dst), "l"(src), "r"(bytes), "r"(bar) : "memory");
}
__device__ __forceinline__ void bulk_store(void* dst, uint32_t src, uint32_t bytes) {
  asm volatile("cp.async.bulk.global.shared::cta.bulk_group [%0], [%1], %2;" ::"l"(dst), "r"(src), "r"(bytes) : "memory");
}
__device__ __forceinline__ void bulk_wait_read() {
  asm volatile("cp.async.bulk.commit_group;\ncp.async.bulk.wait_group.read 0;" ::: "memory");
}

__device__ __forceinline__ void publish(void* dst, uint32_t src, uint32_t bytes, uint32_t bar) {
  bulk_store(dst, src, bytes);
  bulk_wait_read();
  bulk_load(src, dst, bytes, bar);
}

__device__ __forceinline__ void wg_fence() { asm volatile("wgmma.fence.sync.aligned;" ::: "memory"); }
__device__ __forceinline__ void wg_commit() { asm volatile("wgmma.commit_group.sync.aligned;" ::: "memory"); }
template <int N> __device__ __forceinline__ void wg_wait() { asm volatile("wgmma.wait_group.sync.aligned %0;" ::"n"(N) : "memory"); }
__device__ __forceinline__ uint32_t desc_lo(uint32_t addr, uint32_t lbo) { return ((addr & 0x3FFFF) >> 4) | ((lbo >> 4) << 16); }
constexpr uint32_t desc_hi(uint32_t sbo, uint32_t swz) { return (sbo >> 4) | (swz << 30); }
constexpr uint32_t HI_SW128 = desc_hi(1024, 1), HI_SW64 = desc_hi(512, 2), HI_SW32 = desc_hi(256, 3), HI_NONE = desc_hi(128, 0);
template <int N> __device__ __forceinline__ void pin(float* d) {
#pragma unroll
  for (int i = 0; i < N; i++) asm volatile("" : "+f"(d[i])::"memory");
}

__device__ __forceinline__ uint32_t lds32(uint32_t a) {
  uint32_t v;
  asm volatile("ld.volatile.shared.u32 %0, [%1];" : "=r"(v) : "r"(a) : "memory");
  return v;
}
__device__ __forceinline__ uint2 ldg64(const void* a) {
  uint2 v;
  asm volatile("ld.global.nc.v2.u32 {%0, %1}, [%2];" : "=r"(v.x), "=r"(v.y) : "l"(a) : "memory");
  return v;
}
__device__ __forceinline__ void ldsm4(uint32_t* r, uint32_t a) {
  asm volatile("ldmatrix.sync.aligned.m8n8.x4.shared.b16 {%0, %1, %2, %3}, [%4];"
               : "=r"(r[0]), "=r"(r[1]), "=r"(r[2]), "=r"(r[3]) : "r"(a) : "memory");
}
__device__ __forceinline__ void ldsm4t(uint32_t* r, uint32_t a) {
  asm volatile("ldmatrix.sync.aligned.m8n8.x4.trans.shared.b16 {%0, %1, %2, %3}, [%4];"
               : "=r"(r[0]), "=r"(r[1]), "=r"(r[2]), "=r"(r[3]) : "r"(a) : "memory");
}
__device__ __forceinline__ uint2 lds64(uint32_t a) {
  uint2 v;
  asm volatile("ld.shared.v2.u32 {%0, %1}, [%2];" : "=r"(v.x), "=r"(v.y) : "r"(a) : "memory");
  return v;
}
__device__ __forceinline__ uint4 lds128(uint32_t a) {
  uint4 v;
  asm volatile("ld.shared.v4.u32 {%0, %1, %2, %3}, [%4];" : "=r"(v.x), "=r"(v.y), "=r"(v.z), "=r"(v.w) : "r"(a) : "memory");
  return v;
}
__device__ __forceinline__ void sts128(uint32_t a, uint32_t x, uint32_t y, uint32_t z, uint32_t w) {
  asm volatile("st.shared.v4.u32 [%0], {%1, %2, %3, %4};" ::"r"(a), "r"(x), "r"(y), "r"(z), "r"(w) : "memory");
}
__device__ __forceinline__ void stsm4(uint32_t a, const uint32_t* r) {
  asm volatile("stmatrix.sync.aligned.m8n8.x4.shared.b16 [%0], {%1, %2, %3, %4};" ::"r"(a), "r"(r[0]), "r"(r[1]), "r"(r[2]), "r"(r[3]) : "memory");
}
__device__ __forceinline__ uint32_t pack2(float lo, float hi) {
  uint32_t r;
  asm("cvt.rn.bf16x2.f32 %0, %1, %2;" : "=r"(r) : "f"(hi), "f"(lo));
  return r;
}
__device__ __forceinline__ uint32_t movm(uint32_t a) {
  uint32_t d;
  asm volatile("movmatrix.sync.aligned.m8n8.trans.b16 %0, %1;" : "=r"(d) : "r"(a));
  return d;
}
__device__ __forceinline__ uint32_t bmul(uint32_t a, uint32_t b) {
  uint32_t d;
  asm("mul.rn.bf16x2 %0, %1, %2;" : "=r"(d) : "r"(a), "r"(b));
  return d;
}
__device__ __forceinline__ uint32_t badd(uint32_t a, uint32_t b) {
  uint32_t d;
  asm("add.rn.bf16x2 %0, %1, %2;" : "=r"(d) : "r"(a), "r"(b));
  return d;
}
__device__ __forceinline__ uint32_t bfma(uint32_t a, uint32_t b, uint32_t c) {
  uint32_t d;
  asm("fma.rn.bf16x2 %0, %1, %2, %3;" : "=r"(d) : "r"(a), "r"(b), "r"(c));
  return d;
}
__device__ __forceinline__ float bf_lo(uint32_t x) { return __uint_as_float(x << 16); }
__device__ __forceinline__ float bf_hi(uint32_t x) { return __uint_as_float(x & 0xFFFF0000u); }
__device__ __forceinline__ float ex2(float x) {
  float y;
  asm("ex2.approx.ftz.f32 %0, %1;" : "=f"(y) : "f"(x));
  return y;
}
__device__ __forceinline__ float rcp(float x) {
  float y;
  asm("rcp.approx.ftz.f32 %0, %1;" : "=f"(y) : "f"(x));
  return y;
}
__device__ __forceinline__ void mma16816(float* d, uint32_t a0, uint32_t a1, uint32_t a2, uint32_t a3, uint32_t b0, uint32_t b1) {
  asm volatile("mma.sync.aligned.m16n8k16.row.col.f32.bf16.bf16.f32 {%0, %1, %2, %3}, {%4, %5, %6, %7}, {%8, %9}, {%0, %1, %2, %3};"
               : "+f"(d[0]), "+f"(d[1]), "+f"(d[2]), "+f"(d[3])
               : "r"(a0), "r"(a1), "r"(a2), "r"(a3), "r"(b0), "r"(b1));
}
__device__ __forceinline__ void mma1688(float* d, uint32_t a0, uint32_t a1, uint32_t b0) {
  asm volatile("mma.sync.aligned.m16n8k8.row.col.f32.bf16.bf16.f32 {%0, %1, %2, %3}, {%4, %5}, {%6}, {%0, %1, %2, %3};"
               : "+f"(d[0]), "+f"(d[1]), "+f"(d[2]), "+f"(d[3])
               : "r"(a0), "r"(a1), "r"(b0));
}

template <int N> struct WgRS;
template <int N> struct WgSST;
template <> struct WgRS<32> {
  template <uint32_t HB>
  static __device__ __forceinline__ void mma(float* d, const uint32_t* a, uint32_t db) {
    asm volatile("{\n.reg .pred p;\n.reg .b64 db;\nsetp.ne.b32 p, %22, 0;\n"
      "mov.b64 db, {%20, %21};\n"
      "wgmma.mma_async.sync.aligned.m64n32k16.f32.bf16.bf16 {"
      "%0, %1, %2, %3, %4, %5, %6, %7, %8, %9, %10, %11, %12, %13, %14, %15"
      "}, {%16, %17, %18, %19}, db, p, 1, 1, 1;\n}\n"
      : "+f"(d[0]), "+f"(d[1]), "+f"(d[2]), "+f"(d[3]), "+f"(d[4]), "+f"(d[5]), "+f"(d[6]), "+f"(d[7]),
        "+f"(d[8]), "+f"(d[9]), "+f"(d[10]), "+f"(d[11]), "+f"(d[12]), "+f"(d[13]), "+f"(d[14]), "+f"(d[15])
      : "r"(a[0]), "r"(a[1]), "r"(a[2]), "r"(a[3]), "r"(db), "n"(HB), "n"(1));
  }
  template <uint32_t HB>
  static __device__ __forceinline__ void set(float* d, const uint32_t* a, uint32_t db) {
    asm volatile("{\n.reg .pred p;\n.reg .b64 db;\nsetp.ne.b32 p, %22, 0;\n"
      "mov.b64 db, {%20, %21};\n"
      "wgmma.mma_async.sync.aligned.m64n32k16.f32.bf16.bf16 {"
      "%0, %1, %2, %3, %4, %5, %6, %7, %8, %9, %10, %11, %12, %13, %14, %15"
      "}, {%16, %17, %18, %19}, db, p, 1, 1, 1;\n}\n"
      : "=f"(d[0]), "=f"(d[1]), "=f"(d[2]), "=f"(d[3]), "=f"(d[4]), "=f"(d[5]), "=f"(d[6]), "=f"(d[7]),
        "=f"(d[8]), "=f"(d[9]), "=f"(d[10]), "=f"(d[11]), "=f"(d[12]), "=f"(d[13]), "=f"(d[14]), "=f"(d[15])
      : "r"(a[0]), "r"(a[1]), "r"(a[2]), "r"(a[3]), "r"(db), "n"(HB), "n"(0));
  }
};
template <> struct WgRS<64> {
  template <uint32_t HB>
  static __device__ __forceinline__ void mma(float* d, const uint32_t* a, uint32_t db) {
    asm volatile("{\n.reg .pred p;\n.reg .b64 db;\nsetp.ne.b32 p, %38, 0;\n"
      "mov.b64 db, {%36, %37};\n"
      "wgmma.mma_async.sync.aligned.m64n64k16.f32.bf16.bf16 {"
      "%0, %1, %2, %3, %4, %5, %6, %7, %8, %9, %10, %11, %12, %13, %14, %15, "
      "%16, %17, %18, %19, %20, %21, %22, %23, %24, %25, %26, %27, %28, %29, %30, %31"
      "}, {%32, %33, %34, %35}, db, p, 1, 1, 1;\n}\n"
      : "+f"(d[0]), "+f"(d[1]), "+f"(d[2]), "+f"(d[3]), "+f"(d[4]), "+f"(d[5]), "+f"(d[6]), "+f"(d[7]),
        "+f"(d[8]), "+f"(d[9]), "+f"(d[10]), "+f"(d[11]), "+f"(d[12]), "+f"(d[13]), "+f"(d[14]), "+f"(d[15]),
        "+f"(d[16]), "+f"(d[17]), "+f"(d[18]), "+f"(d[19]), "+f"(d[20]), "+f"(d[21]), "+f"(d[22]), "+f"(d[23]),
        "+f"(d[24]), "+f"(d[25]), "+f"(d[26]), "+f"(d[27]), "+f"(d[28]), "+f"(d[29]), "+f"(d[30]), "+f"(d[31])
      : "r"(a[0]), "r"(a[1]), "r"(a[2]), "r"(a[3]), "r"(db), "n"(HB), "n"(1));
  }
  template <uint32_t HB>
  static __device__ __forceinline__ void set(float* d, const uint32_t* a, uint32_t db) {
    asm volatile("{\n.reg .pred p;\n.reg .b64 db;\nsetp.ne.b32 p, %38, 0;\n"
      "mov.b64 db, {%36, %37};\n"
      "wgmma.mma_async.sync.aligned.m64n64k16.f32.bf16.bf16 {"
      "%0, %1, %2, %3, %4, %5, %6, %7, %8, %9, %10, %11, %12, %13, %14, %15, "
      "%16, %17, %18, %19, %20, %21, %22, %23, %24, %25, %26, %27, %28, %29, %30, %31"
      "}, {%32, %33, %34, %35}, db, p, 1, 1, 1;\n}\n"
      : "=f"(d[0]), "=f"(d[1]), "=f"(d[2]), "=f"(d[3]), "=f"(d[4]), "=f"(d[5]), "=f"(d[6]), "=f"(d[7]),
        "=f"(d[8]), "=f"(d[9]), "=f"(d[10]), "=f"(d[11]), "=f"(d[12]), "=f"(d[13]), "=f"(d[14]), "=f"(d[15]),
        "=f"(d[16]), "=f"(d[17]), "=f"(d[18]), "=f"(d[19]), "=f"(d[20]), "=f"(d[21]), "=f"(d[22]), "=f"(d[23]),
        "=f"(d[24]), "=f"(d[25]), "=f"(d[26]), "=f"(d[27]), "=f"(d[28]), "=f"(d[29]), "=f"(d[30]), "=f"(d[31])
      : "r"(a[0]), "r"(a[1]), "r"(a[2]), "r"(a[3]), "r"(db), "n"(HB), "n"(0));
  }
};
template <> struct WgSST<48> {
  template <uint32_t HA, uint32_t HB>
  static __device__ __forceinline__ void mma(float* d, uint32_t da, uint32_t db, int sc) {
    asm volatile("{\n.reg .pred p;\n.reg .b64 da, db;\nsetp.ne.b32 p, %28, 0;\n"
      "mov.b64 da, {%24, %25};\nmov.b64 db, {%26, %27};\n"
      "wgmma.mma_async.sync.aligned.m64n48k16.f32.bf16.bf16 {"
      "%0, %1, %2, %3, %4, %5, %6, %7, %8, %9, %10, %11, %12, %13, %14, %15, "
      "%16, %17, %18, %19, %20, %21, %22, %23"
      "}, da, db, p, 1, 1, 0, 1;\n}\n"
      : "+f"(d[0]), "+f"(d[1]), "+f"(d[2]), "+f"(d[3]), "+f"(d[4]), "+f"(d[5]), "+f"(d[6]), "+f"(d[7]),
        "+f"(d[8]), "+f"(d[9]), "+f"(d[10]), "+f"(d[11]), "+f"(d[12]), "+f"(d[13]), "+f"(d[14]), "+f"(d[15]),
        "+f"(d[16]), "+f"(d[17]), "+f"(d[18]), "+f"(d[19]), "+f"(d[20]), "+f"(d[21]), "+f"(d[22]), "+f"(d[23])
      : "r"(da), "n"(HA), "r"(db), "n"(HB), "r"(sc));
  }
};
template <> struct WgSST<80> {
  template <uint32_t HA, uint32_t HB>
  static __device__ __forceinline__ void mma(float* d, uint32_t da, uint32_t db, int sc) {
    asm volatile("{\n.reg .pred p;\n.reg .b64 da, db;\nsetp.ne.b32 p, %44, 0;\n"
      "mov.b64 da, {%40, %41};\nmov.b64 db, {%42, %43};\n"
      "wgmma.mma_async.sync.aligned.m64n80k16.f32.bf16.bf16 {"
      "%0, %1, %2, %3, %4, %5, %6, %7, %8, %9, %10, %11, %12, %13, %14, %15, "
      "%16, %17, %18, %19, %20, %21, %22, %23, %24, %25, %26, %27, %28, %29, %30, %31, "
      "%32, %33, %34, %35, %36, %37, %38, %39"
      "}, da, db, p, 1, 1, 0, 1;\n}\n"
      : "+f"(d[0]), "+f"(d[1]), "+f"(d[2]), "+f"(d[3]), "+f"(d[4]), "+f"(d[5]), "+f"(d[6]), "+f"(d[7]),
        "+f"(d[8]), "+f"(d[9]), "+f"(d[10]), "+f"(d[11]), "+f"(d[12]), "+f"(d[13]), "+f"(d[14]), "+f"(d[15]),
        "+f"(d[16]), "+f"(d[17]), "+f"(d[18]), "+f"(d[19]), "+f"(d[20]), "+f"(d[21]), "+f"(d[22]), "+f"(d[23]),
        "+f"(d[24]), "+f"(d[25]), "+f"(d[26]), "+f"(d[27]), "+f"(d[28]), "+f"(d[29]), "+f"(d[30]), "+f"(d[31]),
        "+f"(d[32]), "+f"(d[33]), "+f"(d[34]), "+f"(d[35]), "+f"(d[36]), "+f"(d[37]), "+f"(d[38]), "+f"(d[39])
      : "r"(da), "n"(HA), "r"(db), "n"(HB), "r"(sc));
  }
};
template <> struct WgSST<192> {
  template <uint32_t HA, uint32_t HB>
  static __device__ __forceinline__ void mma(float* d, uint32_t da, uint32_t db, int sc) {
    asm volatile("{\n.reg .pred p;\n.reg .b64 da, db;\nsetp.ne.b32 p, %100, 0;\n"
      "mov.b64 da, {%96, %97};\nmov.b64 db, {%98, %99};\n"
      "wgmma.mma_async.sync.aligned.m64n192k16.f32.bf16.bf16 {"
      "%0, %1, %2, %3, %4, %5, %6, %7, %8, %9, %10, %11, %12, %13, %14, %15, "
      "%16, %17, %18, %19, %20, %21, %22, %23, %24, %25, %26, %27, %28, %29, %30, %31, "
      "%32, %33, %34, %35, %36, %37, %38, %39, %40, %41, %42, %43, %44, %45, %46, %47, "
      "%48, %49, %50, %51, %52, %53, %54, %55, %56, %57, %58, %59, %60, %61, %62, %63, "
      "%64, %65, %66, %67, %68, %69, %70, %71, %72, %73, %74, %75, %76, %77, %78, %79, "
      "%80, %81, %82, %83, %84, %85, %86, %87, %88, %89, %90, %91, %92, %93, %94, %95"
      "}, da, db, p, 1, 1, 0, 1;\n}\n"
      : "+f"(d[0]), "+f"(d[1]), "+f"(d[2]), "+f"(d[3]), "+f"(d[4]), "+f"(d[5]), "+f"(d[6]), "+f"(d[7]),
        "+f"(d[8]), "+f"(d[9]), "+f"(d[10]), "+f"(d[11]), "+f"(d[12]), "+f"(d[13]), "+f"(d[14]), "+f"(d[15]),
        "+f"(d[16]), "+f"(d[17]), "+f"(d[18]), "+f"(d[19]), "+f"(d[20]), "+f"(d[21]), "+f"(d[22]), "+f"(d[23]),
        "+f"(d[24]), "+f"(d[25]), "+f"(d[26]), "+f"(d[27]), "+f"(d[28]), "+f"(d[29]), "+f"(d[30]), "+f"(d[31]),
        "+f"(d[32]), "+f"(d[33]), "+f"(d[34]), "+f"(d[35]), "+f"(d[36]), "+f"(d[37]), "+f"(d[38]), "+f"(d[39]),
        "+f"(d[40]), "+f"(d[41]), "+f"(d[42]), "+f"(d[43]), "+f"(d[44]), "+f"(d[45]), "+f"(d[46]), "+f"(d[47]),
        "+f"(d[48]), "+f"(d[49]), "+f"(d[50]), "+f"(d[51]), "+f"(d[52]), "+f"(d[53]), "+f"(d[54]), "+f"(d[55]),
        "+f"(d[56]), "+f"(d[57]), "+f"(d[58]), "+f"(d[59]), "+f"(d[60]), "+f"(d[61]), "+f"(d[62]), "+f"(d[63]),
        "+f"(d[64]), "+f"(d[65]), "+f"(d[66]), "+f"(d[67]), "+f"(d[68]), "+f"(d[69]), "+f"(d[70]), "+f"(d[71]),
        "+f"(d[72]), "+f"(d[73]), "+f"(d[74]), "+f"(d[75]), "+f"(d[76]), "+f"(d[77]), "+f"(d[78]), "+f"(d[79]),
        "+f"(d[80]), "+f"(d[81]), "+f"(d[82]), "+f"(d[83]), "+f"(d[84]), "+f"(d[85]), "+f"(d[86]), "+f"(d[87]),
        "+f"(d[88]), "+f"(d[89]), "+f"(d[90]), "+f"(d[91]), "+f"(d[92]), "+f"(d[93]), "+f"(d[94]), "+f"(d[95])
      : "r"(da), "n"(HA), "r"(db), "n"(HB), "r"(sc));
  }
};

struct FftConst {
  uint32_t f[2][4], fi[4][4];
  uint32_t ta[2][2], tb[2][2];
};
__device__ __forceinline__ void cis(int m, float scale, float& c, float& s) {
  const float a = (float)m * (-6.283185307179586f * scale);
  c = __cosf(a);
  s = __sinf(a);
}
__device__ __forceinline__ void fft_tables(uint32_t (&v)[12], int tw) {
  const int row = tw >> 2, ch = tw & 3;
#pragma unroll
  for (int i = 0; i < 4; i++) {
    float c[2], s[2], x[2];
#pragma unroll
    for (int e = 0; e < 2; e++) {
      cis((((32 * (8 * ch + 2 * i + e) + 15) * (4 * row - 63) + 2048) & 4095) - 2048, 1.f / 4096, c[e], s[e]);
      float gc, gs;
      cis((((row & 15) * (8 * (ch & 1) + 2 * i + e) + 8) & 15) - 8, 1.f / 16, gc, gs);
      x[e] = (row >> 4) == (ch >> 1) ? gc : (ch >> 1) ? gs : -gs;
    }
    v[i] = pack2(c[0] * 0.125f, c[1] * 0.125f);
    v[4 + i] = pack2(s[0] * 0.125f, s[1] * 0.125f);
    v[8 + i] = pack2(x[0], x[1]);
  }
#pragma unroll
  for (int i = 0; i < 12; i++) asm volatile("" : "+r"(v[i]));
}
__device__ __forceinline__ void fft_tables_store(const uint32_t (&v)[12], uint32_t sb, int tw) {
  const int row = tw >> 2;
  const uint32_t x = ((tw ^ (row >> 1)) & 3) << 4, a = sb + OFF_FT + (16 * (row >> 3) + (row & 7)) * 64 + x;
  sts128(a, v[0], v[1], v[2], v[3]);
  sts128(a + 512, v[4], v[5], v[6], v[7]);
  sts128(sb + OFF_GT + row * 64 + x, v[8], v[9], v[10], v[11]);
}
__device__ __forceinline__ void fft_twiddles(uint32_t (&v)[2], int tw) {
  float a[2], s[2];
#pragma unroll
  for (int i = 0; i < 2; i++) {
    float c;
    cis((2 * (2 * (tw & 3) + i) - 15) * (4 * (tw >> 2) - 63), 1.f / 4096, c, s[i]);
    a[i] = __fdividef(-s[i], 1.f + c);
  }
  v[0] = pack2(a[0], a[1]);
  v[1] = pack2(s[0], s[1]);
  asm volatile("" : "+r"(v[0]), "+r"(v[1]));
}
__device__ __forceinline__ void fft_matrices(FftConst& k, uint32_t sb, int w, int lane) {
  const uint32_t x = (lane >> 1) & 3;
  const uint2 t0 = lds64(sb + OFF_TT + 256 * w + 8 * lane), t1 = lds64(sb + OFF_TT + 256 * w + 8 * (lane ^ 3));
  k.ta[0][0] = t0.x;
  k.tb[0][0] = t0.y;
  k.ta[1][1] = __byte_perm(t1.x, 0, 0x1032);
  k.tb[1][1] = __byte_perm(t1.y, 0, 0x1032);
#pragma unroll
  for (int j = 0; j < 2; j++) {
    k.ta[1 - j][j] = k.ta[j][j] ^ 0x80008000u;
    k.tb[1 - j][j] = k.tb[j][j] ^ 0x80008000u;
    asm volatile("" : "+r"(k.ta[0][j]), "+r"(k.tb[0][j]), "+r"(k.ta[1][j]), "+r"(k.tb[1][j]));
  }
#pragma unroll
  for (int i = 0; i < 2; i++) {
    ldsm4(k.f[i], sb + OFF_FT + (16 * w + (lane & 15)) * 64 + (((2 * i + (lane >> 4)) ^ x) << 4));
    ldsm4t(k.fi[i], sb + OFF_FT + (32 * i + lane) * 64 + ((w ^ x) << 4));
#pragma unroll
    for (int j = 0; j < 4; j++) {
      k.fi[2 + i][j] = (j & 1) ? k.fi[i][j - 1] ^ 0x80008000u : k.fi[i][j + 1];
      asm volatile("" : "+r"(k.fi[2 + i][j]));
    }
  }
}
__device__ __forceinline__ void rot(uint32_t& x, uint32_t& y, uint32_t a, uint32_t b) {
  x = bfma(a, y, x);
  y = bfma(b, x, y);
  x = bfma(a, y, x);
}
__device__ __forceinline__ void twiddle_fwd(uint32_t (&a)[4][4], float* d, const FftConst& k) {
#pragma unroll
  for (int q = 0; q < 4; q++)
#pragma unroll
    for (int j = 0; j < 2; j++) {
      const float* x = d + 8 * q + 4 * j;
      uint32_t re = pack2(x[0], x[1]), im = pack2(x[2], x[3]);
      rot(re, im, k.ta[0][j], k.tb[0][j]);
      a[q & 2][2 * j + (q & 1)] = re;
      a[(q & 2) + 1][2 * j + (q & 1)] = im;
    }
}
__device__ __forceinline__ void g_step(float* d, const uint32_t (&a)[4][4], uint32_t dre, uint32_t dim) {
  WgRS<32>::set<HI_SW64>(d, a[0], dre);
  WgRS<32>::set<HI_SW64>(d + 16, a[2], dre);
  WgRS<32>::mma<HI_SW64>(d, a[1], dim);
  WgRS<32>::mma<HI_SW64>(d + 16, a[3], dim);
  wg_commit();
}

__device__ __forceinline__ void products(uint32_t (&a)[4][4], const float* H, const float* U, int p) {
#pragma unroll
  for (int j = 0; j < 2; j++)
#pragma unroll
    for (int m = 2 * p; m < 2 * p + 2; m++) {
      float pr[2], pi[2];
#pragma unroll
      for (int x = 0; x < 2; x++)
#pragma unroll
        for (int q = 0; q <= m; q++) {
          const int ih = 16 * (q >> 1) + 2 * (q & 1) + 4 * j + x, iu = 16 * ((m - q) >> 1) + 2 * ((m - q) & 1) + 4 * j + x;
          pr[x] = q ? fmaf(H[ih], U[iu], pr[x]) : H[ih] * U[iu];
          pi[x] = q ? fmaf(H[ih], U[iu + 8], pi[x]) : H[ih] * U[iu + 8];
          pr[x] = fmaf(-H[ih + 8], U[iu + 8], pr[x]);
          pi[x] = fmaf(H[ih + 8], U[iu], pi[x]);
        }
      a[m & 2][2 * j + (m & 1)] = pack2(pr[0], pr[1]);
      a[(m & 2) + 1][2 * j + (m & 1)] = pack2(pi[0], pi[1]);
    }
}

__device__ __forceinline__ void conv_channel(const FftConst& k, uint32_t sb, int c, int wg, int w, int lane) {
  const uint32_t cb = sb + off_ch(c), bars = sb + OFF_BAR;
  const uint32_t du = desc_lo(cb, 1024), dg = desc_lo(sb + OFF_GT, 16), dz = desc_lo(cb + U_BYTES, 16);
  float U[32], H[32];
  uint32_t a[4][4], e[4][4];
  const float dv = __uint_as_float(lds32(sb + OFF_D + 4 * c));
  wg_fence();
  WgRS<64>::set<HI_SW32>(H, k.f[0], du + 256);
  WgRS<64>::mma<HI_SW32>(H, k.f[1], du + 256 + 32);
  wg_commit();
  wg_wait<0>();
  pin<32>(H);
  twiddle_fwd(a, H, k);
  mbar_wait(bars + 8 * (B_U + (c < 3 ? c : 3)), 0);
  TSM(w == 0 && c < 3, 7 + wg);
  wg_fence();
  WgRS<64>::set<HI_SW32>(U, k.f[0], du);
  WgRS<64>::mma<HI_SW32>(U, k.f[1], du + 32);
  wg_commit();
  g_step(H, a, dg, dg + 64);
  wg_wait<1>();
  pin<32>(U);
  twiddle_fwd(e, U, k);
  wg_fence();
  g_step(U, e, dg, dg + 64);
  wg_wait<0>();
  pin<32>(U);
  pin<32>(H);
#pragma unroll
  for (int j = 0; j < 4; j++) H[4 * (j >> 1) + (j & 1)] += dv;
  float V[32];
#pragma unroll
  for (int p = 0; p < 2; p++) {
    products(a, H, U, p);
    wg_fence();
    WgRS<32>::set<HI_SW64>(V + 16 * p, a[2 * p], dg + 64);
    WgRS<32>::mma<HI_SW64>(V + 16 * p, a[2 * p + 1], dg);
    wg_commit();
  }
  const uint32_t za = cb + U_BYTES + (8 * w + (lane & 7)) * 128 + (((lane >> 3) ^ (lane & 7)) << 4);
  const uint32_t ya = cb + (lane >> 4) * 1024 + (8 * w + (lane & 7)) * 32 + ((((lane >> 3) ^ (lane >> 2)) & 1) << 4);
  wg_sync(1 + wg);
#pragma unroll
  for (int p = 0; p < 2; p++) {
    if (p == 0) wg_wait<1>();
    else wg_wait<0>();
    pin<16>(V + 16 * p);
#pragma unroll
    for (int i = 0; i < 4; i++) {
      const int j = i & 1;
      const float* x = V + 16 * p + 4 * j + (i & 2);
      e[p][i] = pack2(x[8], x[9]);
      e[2 + p][i] = pack2(x[0], x[1]);
      rot(e[p][i], e[2 + p][i], k.ta[1][j], k.tb[1][j]);
    }
    stsm4(za ^ (64 * p), e[p]);
    stsm4((za ^ (64 * p)) + 4096, e[2 + p]);
  }
  fence_async_smem();
  wg_sync(1 + wg);
  wg_fence();
  WgRS<64>::set<HI_SW128>(H, k.fi[0], dz);
#pragma unroll
  for (int ks = 1; ks < 4; ks++) WgRS<64>::mma<HI_SW128>(H, k.fi[ks], dz + 128 * ks);
  wg_commit();
  wg_wait<0>();
  pin<32>(H);
  if (lane == 0) mbar_arrive(bars + 8 * B_CVD);
  TSIF(w == 0, 88 + c);
#pragma unroll
  for (int j = 0; j < 8; j++)
    a[j >> 2][j & 3] = j < 2 ? pack2(H[4 * j], H[4 * j + 1]) : pack2(H[4 * j] + H[4 * j - 6], H[4 * j + 1] + H[4 * j - 5]);
  stsm4(ya, a[0]);
  stsm4(ya + 2048, a[1]);
  fence_async_smem();
  __syncwarp();
}

__device__ __forceinline__ void prep_slab(uint4* res, const uint2* sw, uint32_t sb, int slab, int w, int lane) {
  const int t = lane & 3, tp = (lane & 7) >> 1, pos = 8 * tp + 2 * (((lane >> 3) + tp) & 3) + (lane & 1);
  const uint32_t base = sb + OFF_KVS + slab * KVS_BYTES + pos * 128;
  uint32_t kk[2][4][4], vv[2][4];
  mbar_wait(sb + OFF_BAR + 8 * (B_KV + slab), 0);
#pragma unroll
  for (int h = 0; h < 2; h++) {
#pragma unroll
    for (int j = 0; j < 4; j++) {
      const uint32_t a = base + 128 * j;
      ldsm4t(kk[h][j], a + (((w + 4 * h) ^ ((a >> 7) & 7)) << 4));
    }
    const uint32_t a = base + KVS_V;
    ldsm4t(vv[h], a + (((w + 4 * h) ^ ((a >> 7) & 7)) << 4));
  }
#pragma unroll
  for (int h = 0; h < 2; h++) {
    uint32_t (&k)[4][4] = kk[h];
    uint32_t (&v)[4] = vv[h];
    const uint32_t w0 = __byte_perm(sw[h].x, 0, 0x1010), w1 = __byte_perm(sw[h].x, 0, 0x3232);
    const uint32_t w2 = __byte_perm(sw[h].y, 0, 0x1010), w3 = __byte_perm(sw[h].y, 0, 0x3232);
#pragma unroll
    for (int m = 0; m < 4; m++)
      v[m] = bmul(badd(badd(badd(bmul(k[0][m], w3), bmul(k[1][m], w2)), bmul(k[2][m], w1)), bmul(k[3][m], w0)), v[m]);
    uint32_t a[4];
#pragma unroll
    for (int m = 0; m < 4; m++) a[m] = (t & 1) ? v[(m + 3) & 3] : v[m];
    res[h] = (t & 2) ? make_uint4(a[2], a[3], a[0], a[1]) : make_uint4(a[0], a[1], a[2], a[3]);
  }
}

__device__ __forceinline__ void prep_gate(const Params& p, uint32_t sb, int b, int w, int lane) {
  uint2 gw[5], x[4][5];
#pragma unroll
  for (int j = 0; j < 5; j++) gw[j] = ldg64(reinterpret_cast<const uint2*>(p.gate_w) + lane + 32 * j);
#pragma unroll
  for (int i = 0; i < 4; i++)
#pragma unroll
    for (int j = 0; j < 5; j++)
      x[i][j] = ldg64(reinterpret_cast<const uint2*>(p.q) + (16 * b + 4 * w + i) * (DIM / 4) + lane + 32 * j);
  float s[4];
#pragma unroll
  for (int i = 0; i < 4; i++) {
    s[i] = 0.f;
#pragma unroll
    for (int j = 0; j < 5; j++) {
      const uint32_t m0 = bmul(x[i][j].x, gw[j].x), m1 = bmul(x[i][j].y, gw[j].y);
      s[i] += (bf_lo(m0) + bf_hi(m0)) + (bf_lo(m1) + bf_hi(m1));
    }
  }
  const bool h = lane & 16, q = lane & 8;
  const float a = (h ? s[2] : s[0]) + __shfl_xor_sync(0xffffffffu, h ? s[0] : s[2], 16);
  const float c = (h ? s[3] : s[1]) + __shfl_xor_sync(0xffffffffu, h ? s[1] : s[3], 16);
  float z = (q ? c : a) + __shfl_xor_sync(0xffffffffu, q ? a : c, 8);
#pragma unroll
  for (int o = 4; o > 0; o >>= 1) z += __shfl_xor_sync(0xffffffffu, z, o);
  z = bf_lo(pack2(z, 0.f));
  z = bf_lo(pack2(__fdividef(1.f, 1.f + __expf(-z)), 0.f));
  mbar_wait(sb + OFF_BAR + 8 * B_S3, 0);
  if ((lane & 7) == 0) asm volatile("st.shared.f32 [%0], %1;" ::"r"(sb + OFF_GATE + 64 * (b & 7) + 16 * w + (lane >> 1)), "f"(z) : "memory");
  fence_async_smem();
}

__device__ __forceinline__ uint32_t bmax(uint32_t a, uint32_t b) {
  uint32_t d;
  asm("max.bf16x2 %0, %1, %2;" : "=r"(d) : "r"(a), "r"(b));
  return d;
}
__device__ __forceinline__ void softmax_two(const float (&l)[2][2], uint32_t& p0, uint32_t& p1) {
  constexpr float kScale = 0.22360679774997896f, kLog2e = 1.4426950408889634f;
  const uint32_t r0 = pack2(l[0][0], l[1][0]), r1 = pack2(l[0][1], l[1][1]);
  const uint32_t x0 = pack2(bf_lo(r0) * kScale, bf_hi(r0) * kScale), x1 = pack2(bf_lo(r1) * kScale, bf_hi(r1) * kScale);
  uint32_t m = bmax(x0, x1);
  m = bmax(m, __shfl_xor_sync(0xffffffffu, m, 1));
  m = bmax(m, __shfl_xor_sync(0xffffffffu, m, 2));
  const float m0 = bf_lo(m) * kLog2e, m1 = bf_hi(m) * kLog2e;
  p0 = pack2(ex2(bf_lo(x0) * kLog2e - m0), ex2(bf_lo(x1) * kLog2e - m0));
  p1 = pack2(ex2(bf_hi(x0) * kLog2e - m1), ex2(bf_hi(x1) * kLog2e - m1));
}

__device__ __forceinline__ void halo_read(uint32_t (&kpv)[10], uint32_t (&vpv)[10], uint32_t (&tg)[7], const uint4* hp) {
#pragma unroll
  for (int j = 0; j < 7; j++) {
    uint32_t x0, x1, x2;
    asm volatile("ld.relaxed.gpu.global.v4.u32 {%0, %1, %2, %3}, [%4];"
                 : "=r"(x0), "=r"(x1), "=r"(x2), "=r"(tg[j]) : "l"(hp + 32 * j) : "memory");
    if (j < 4) kpv[3 * j] = x0; else vpv[3 * j - 10] = x0;
    if (j < 3) kpv[3 * j + 1] = x1; else vpv[3 * j - 9] = x1;
    if (j < 3) kpv[3 * j + 2] = x2; else if (j < 6) vpv[3 * j - 8] = x2;
  }
}

template <int ROT>
__device__ __forceinline__ void pack_qkv(const float* acc, uint32_t (&qlo)[10], uint32_t (&qhi)[10], uint32_t (&klo)[10],
                                         uint32_t (&khi)[10], uint32_t (&vlo)[10], uint32_t (&vhi)[10]) {
#pragma unroll
  for (int j = 0; j < 10; j++) {
    const int x = (j + ROT) % 10, tq = x < 8 ? x : 16 + x, tk = x < 8 ? 8 + x : 18 + x, tv = x < 8 ? 16 + x : 20 + x;
    khi[j] = pack2(acc[4 * tk + 2], acc[4 * tk + 3]);
    vhi[j] = movm(pack2(acc[4 * tv + 2], acc[4 * tv + 3]));
    qlo[j] = pack2(acc[4 * tq], acc[4 * tq + 1]);
    qhi[j] = pack2(acc[4 * tq + 2], acc[4 * tq + 3]);
    klo[j] = pack2(acc[4 * tk], acc[4 * tk + 1]);
    vlo[j] = pack2(acc[4 * tv], acc[4 * tv + 1]);
    asm volatile("" : "+r"(khi[j]), "+r"(qlo[j]), "+r"(qhi[j]), "+r"(klo[j]), "+r"(vlo[j]));
  }
}

template <int ROT> __device__ __forceinline__ void halo_send(const float* acc, uint4* ho, uint32_t tag) {
#pragma unroll
  for (int j = 0; j < 7; j++) {
    uint32_t x[3];
#pragma unroll
    for (int e = 0; e < 3; e++) {
      const int i = 3 * j + e, y = (i % 10 + ROT) % 10, tk = y < 8 ? 8 + y : 18 + y, tv = y < 8 ? 16 + y : 20 + y;
      x[e] = i < 10 ? pack2(acc[4 * tk + 2], acc[4 * tk + 3]) : i < 20 ? movm(pack2(acc[4 * tv + 2], acc[4 * tv + 3])) : 0u;
    }
    asm volatile("st.relaxed.gpu.global.v4.u32 [%0], {%1, %2, %3, %4};" ::"l"(ho + 32 * j), "r"(x[0]), "r"(x[1]), "r"(x[2]), "r"(tag) : "memory");
  }
}

__device__ __forceinline__ void attention(float* acc, uint32_t sb, int b, int par, int w, int lane, uint32_t tag) {
  const int g = lane >> 2, t = lane & 3;
  uint32_t klo[10], khi[10], vlo[10], vhi[10], qlo[10], qhi[10], kpv[10], vpv[10];
  if (w == 3 && b < NCTA - 8) {
    uint4* ho = g_halo + (b * 2 + par) * 224 + lane;
    if (tail_first(b & 7)) halo_send<8>(acc, ho, tag);
    else halo_send<0>(acc, ho, tag);
    TSIF(par == 0, 76);
    pin<120>(acc);
  }
  if (tail_first(b & 7)) pack_qkv<8>(acc, qlo, qhi, klo, khi, vlo, vhi);
  else pack_qkv<0>(acc, qlo, qhi, klo, khi, vlo, vhi);
  const uint32_t xa = sb + OFF_KVX + (par * 3) * 2560 + lane * 16;
  if (w < 3) {
    sts128(xa + w * 2560, khi[0], khi[1], khi[2], khi[3]);
    sts128(xa + w * 2560 + 512, khi[4], khi[5], khi[6], khi[7]);
    sts128(xa + w * 2560 + 1024, khi[8], khi[9], vhi[0], vhi[1]);
    sts128(xa + w * 2560 + 1536, vhi[2], vhi[3], vhi[4], vhi[5]);
    sts128(xa + w * 2560 + 2048, vhi[6], vhi[7], vhi[8], vhi[9]);
  }
  TSIF(par == 0 && w == 1, 64);
#pragma unroll
  for (int j = 0; j < 10; j++) vlo[j] = movm(vlo[j]);
  const bool far0 = 2 * t > g, far1 = 2 * t + 1 > g;
  const uint32_t mfar = (far0 ? 0x0000FFFFu : 0u) | (far1 ? 0xFFFF0000u : 0u);
  float slo[4][2], lg[2][2];
  uint32_t phi[4], plo[4], qml[4], qmh[4];
#pragma unroll
  for (int h = 0; h < 4; h++) {
    const int f = h == 0 ? 0 : h == 1 ? 3 : h == 2 ? 5 : 8, hf = h < 2 ? 2 : 7;
    const bool mine = (h & 1) ? t >= 2 : t < 2;
    qml[h] = mine ? qlo[hf] : 0u;
    qmh[h] = mine ? qhi[hf] : 0u;
    float a[4] = {0.f, 0.f, 0.f, 0.f}, c[4] = {0.f, 0.f, 0.f, 0.f};
    mma16816(a, qlo[f], qhi[f], qlo[f + 1], qhi[f + 1], klo[f], klo[f + 1]);
    mma16816(c, qlo[f], qhi[f], qlo[f + 1], qhi[f + 1], khi[f], khi[f + 1]);
    mma1688(a, qml[h], qmh[h], klo[hf]);
    mma1688(c, qml[h], qmh[h], khi[hf]);
    slo[h][0] = a[0];
    slo[h][1] = a[1];
    lg[h & 1][0] = far0 ? a[2] : c[2];
    lg[h & 1][1] = far1 ? a[3] : c[3];
    if (h & 1) softmax_two(lg, phi[h - 1], phi[h]);
  }
  TSIF(par == 0 && w == 1, 65);
  wg_sync(1 + par);
  TSIF(par == 0 && w == 1, 66);
  const bool nohist = (w == 0) && (b < 8);
  const uint4* hp = g_halo + ((b - 8) * 2 + par) * 224 + lane;
  uint32_t tg[7];
  if (w > 0) {
    const uint4 v0 = lds128(xa + (w - 1) * 2560), v1 = lds128(xa + (w - 1) * 2560 + 512), v2 = lds128(xa + (w - 1) * 2560 + 1024);
    const uint4 v3 = lds128(xa + (w - 1) * 2560 + 1536), v4 = lds128(xa + (w - 1) * 2560 + 2048);
    kpv[0] = v0.x; kpv[1] = v0.y; kpv[2] = v0.z; kpv[3] = v0.w; kpv[4] = v1.x; kpv[5] = v1.y; kpv[6] = v1.z; kpv[7] = v1.w;
    kpv[8] = v2.x; kpv[9] = v2.y; vpv[0] = v2.z; vpv[1] = v2.w; vpv[2] = v3.x; vpv[3] = v3.y; vpv[4] = v3.z; vpv[5] = v3.w;
    vpv[6] = v4.x; vpv[7] = v4.y; vpv[8] = v4.z; vpv[9] = v4.w;
  } else if (nohist) {
#pragma unroll
    for (int j = 0; j < 10; j++) kpv[j] = vpv[j] = 0u;
  } else {
    TSIF(par == 0, 77);
    halo_read(kpv, vpv, tg, hp);
  }
  if (w == 0 && !nohist) {
    int spins = 0;
    while (true) {
      bool ok = true;
#pragma unroll
      for (int j = 0; j < 7; j++) ok = ok && tg[j] == tag;
      if (__all_sync(0xffffffffu, ok) || ++spins > SPIN_LIMIT) break;
      halo_read(kpv, vpv, tg, hp);
    }
    TSIF(par == 0, 79);
  }
#pragma unroll
  for (int h = 0; h < 4; h++) {
    const int f = h == 0 ? 0 : h == 1 ? 3 : h == 2 ? 5 : 8, hf = h < 2 ? 2 : 7;
    float a[4] = {0.f, 0.f, 0.f, 0.f};
    mma16816(a, qlo[f], qhi[f], qlo[f + 1], qhi[f + 1], kpv[f], kpv[f + 1]);
    mma1688(a, qml[h], qmh[h], kpv[hf]);
    const float ninf = __int_as_float(0xff800000);
    lg[h & 1][0] = far0 ? (nohist ? ninf : a[0]) : slo[h][0];
    lg[h & 1][1] = far1 ? (nohist ? ninf : a[1]) : slo[h][1];
    if (h & 1) softmax_two(lg, plo[h - 1], plo[h]);
  }
  TSIF(par == 0 && w <= 1, 67 + w);
  uint32_t ov[20];
#pragma unroll
  for (int hp = 0; hp < 2; hp++) {
    const int hf = hp ? 7 : 2;
    float sh[4] = {0.f, 0.f, 0.f, 0.f}, i0 = 0.f, i1 = 0.f;
#pragma unroll
    for (int e = 0; e < 2; e++) {
      const int h = 2 * hp + e, f = h == 0 ? 0 : h == 1 ? 3 : h == 2 ? 5 : 8;
      const uint32_t a0 = plo[h] & mfar, a2 = plo[h] & ~mfar, a3 = phi[h] & mfar, c1 = phi[h] & ~mfar;
      float sum[4] = {0.f, 0.f, 0.f, 0.f};
      mma1688(sum, plo[h], phi[h], 0x3F803F80u);
      const float r0 = rcp(sum[0]), r1 = rcp(sum[2]);
#pragma unroll
      for (int j = f; j < f + 2; j++) {
        float o[4] = {0.f, 0.f, 0.f, 0.f};
        mma16816(o, a0, 0u, a2, a3, vpv[j], vlo[j]);
        mma1688(o, 0u, c1, vhi[j]);
        ov[2 * j] = pack2(o[0] * r0, o[1] * r0);
        ov[2 * j + 1] = pack2(o[2] * r1, o[3] * r1);
      }
      const bool mine = e ? g >= 4 : g < 4;
      mma16816(sh, a0, 0u, a2, a3, mine ? vpv[hf] : 0u, mine ? vlo[hf] : 0u);
      mma1688(sh, 0u, c1, mine ? vhi[hf] : 0u);
      if (e == 0 || t >= 2) {
        i0 = r0;
        i1 = r1;
      }
    }
    ov[2 * hf] = pack2(sh[0] * i0, sh[1] * i0);
    ov[2 * hf + 1] = pack2(sh[2] * i1, sh[3] * i1);
  }
  TS(32 + 4 * par + w);
  mbar_wait(sb + OFF_BAR + 8 * B_P1, 0);
  const uint32_t oa = sb + OFF_OA + (lane >> 4) * 2048 + (32 * w + 2 * (lane & 15) + par) * 16;
#pragma unroll
  for (int j = 0; j < 5; j++) stsm4(oa + 4096 * j, ov + 4 * j);
  TSIF(par == 0 && w == 0, 120);
  fence_async_smem();
  TSIF(par == 0 && w == 0, 121);
  __syncwarp();
  if (lane == 0) mbar_arrive(sb + OFF_BAR + 8 * B_ATTN);
  TSM(w == 0 || w == 2, 122 + par + (w == 2 ? 3 : 0));
}

struct Maps {
  CUtensorMap x, wm, wt, k, v, y, wo, qm, qt, om, ot, yl, ol, ye;
};

__device__ __forceinline__ void load_stage(uint32_t sb, int kb, int b, const Maps& m) {
  const uint32_t st = sb + (kb & 3) * STAGE_BYTES, bar = sb + OFF_BAR + 8 * (B_FULL1 + (kb & 3));
  const int r = b >> 3, hg = b & 7, slab = kb - KV_KB;
  const bool kv = slab >= 0 && slab < 5;
  const uint32_t kbar = sb + OFF_BAR + 8 * (B_KV + slab), dst = sb + OFF_KVS + slab * KVS_BYTES;
  mbar_expect_tx(bar, STAGE_BYTES);
  if (kv) mbar_expect_tx(kbar, KVS_BYTES);
  tma_3d(st, &m.x, 64 * kb, 64 * r, 0, bar);
  tma_3d(st + ST_W, &m.wm, 80 * hg + (tail_first(hg) ? 16 : 0), 64 * kb, 0, bar);
  tma_3d(st + ST_WT, &m.wt, 80 * hg + (tail_first(hg) ? 0 : 64), 64 * kb, 0, bar);
  if (kv) tma_3d(dst, &m.k, 0, 32 * (b >> 1) - 3, 2 * slab + (b & 1), kbar);
  if (kv) tma_3d(dst + KVS_V, &m.v, 0, 32 * (b >> 1), 2 * slab + (b & 1), kbar);
}

__global__ void __launch_bounds__(NTHR, 1) fused_kernel(const __grid_constant__ Maps m, const Params p) {
  extern __shared__ __align__(1024) uint8_t smem[];
  const uint32_t sb = (uint32_t)__cvta_generic_to_shared(smem);
  const uint32_t bars = sb + OFF_BAR;
  const int tid = threadIdx.x, lane = tid & 31;
  int b = blockIdx.x;
  b = (((b & 63) >> 3) * 2 + (b & 1)) * 8 + (((b < 64 ? 0x6521 : 0x7430) >> (4 * ((b >> 1) & 3))) & 7);
  const int r = b >> 3, hg = b & 7;

  if (tid == T_ISSUE) {
    TSM(true, 0);
    mbar_init(bars + 8 * B_F0, 1);
    fence_async_smem();
    mbar_expect_tx(bars + 8 * B_F0, ST_WT);
    tma_3d(sb, &m.x, 0, 64 * r, 0, bars + 8 * B_F0);
    tma_3d(sb + ST_W, &m.wm, 80 * hg + (tail_first(hg) ? 16 : 0), 0, 0, bars + 8 * B_F0);
#pragma unroll
    for (int i = 0; i < 4; i++) mbar_init(bars + 8 * (B_FULL1 + i), 1);
    fence_async_smem();
    mbar_expect_tx(bars + 8 * B_FULL1, STAGE_BYTES - ST_WT);
    tma_3d(sb + ST_WT, &m.wt, 80 * hg + (tail_first(hg) ? 0 : 64), 0, 0, bars + 8 * B_FULL1);
    load_stage(sb, 1, b, m);
  } else if (tid == T_INIT) {
#pragma unroll
    for (int i = 0; i < B_F0; i++) mbar_init(bars + 8 * i, i < B_GATE ? 8 : i < B_CVD ? 4 : i == B_CVD ? 20 : 1);
    fence_async_smem();
  }
  const int warp = __shfl_sync(0xffffffffu, tid >> 5, 0), wg = warp >> 2, w = warp & 3;
  __syncthreads();

  if (wg == 3) {
    asm volatile("setmaxnreg.dec.sync.aligned.u32 56;");
    if (w == 0) {
      if (lane == 0) {
#pragma unroll 1
        for (int kb = 2; kb < 10; kb++) {
          if (kb >= 4) mbar_wait(bars + 8 * (kb == 7 ? B_E3 : B_EMPTY1 + (kb & 3)), (kb >> 3) & 1);
          TSIF(kb >= 4, 44 + kb);
          load_stage(sb, kb, b, m);
          TSIF(kb == 3, 60);
          if (kb == TRIG_KB) mbar_arrive(bars + 8 * B_LAST);
        }
        mbar_wait(bars + 8 * B_WOP, 0);
        mbar_wait(bars + 8 * WL_TRIG, 0);
        mbar_wait(bars + 8 * B_EPOCH, 0);
        flag_wait(g_cnt + C_W + 32 * hg, (lds32(sb + OFF_EPOCH) + 1) * 16);
        TS(30);
#pragma unroll 1
        for (int j = 0; j < 8; j++) {
          if (j >= 6) mbar_wait(bars + 8 * (W_LATE ? B_YRB : B_EMPTY2 + j - 6), 0);
          if (j == 4) mbar_wait(bars + 8 * (RB32 & 2 ? B_ORB : B_ATTN), 0);
          TSIF(j >= 6, 100 + j);
          mbar_expect_tx(bars + 8 * (B_FULL2 + j), j == 0 ? WO_BYTES : j == 5 ? O_BYTES + WO_BYTES + 512 : O_BYTES + WO_BYTES);
          bulk_load(sb + off_w(j), g_WO + (hg * 8 + step_src(hg, j)) * 800, WO_BYTES, bars + 8 * (B_FULL2 + j));
        }
        mbar_wait(bars + 8 * (B_EMPTY2 + 3), 0);
        mbar_expect_tx(bars + 8 * B_QF, O_BYTES);
        tma_2d(sb + OFF_QS, &m.qm, 80 * hg, 128 * r, bars + 8 * B_QF);
        tma_2d(sb + OFF_QT, &m.qt, 80 * hg + 64, 128 * r, bars + 8 * B_QF);
      }
    } else if (w == 1) {
      unsigned epoch = 0;
      if (lane == 0) {
        epoch = atomicAdd(g_cnt + C_LAUNCH, 1u) / NCTA;
        asm volatile("st.shared.u32 [%0], %1;" ::"r"(sb + OFF_EPOCH), "r"(epoch) : "memory");
        mbar_arrive(bars + 8 * B_EPOCH);
        mbar_wait(bars + 8 * B_KVD, 0);
        mbar_expect_tx(bars + 8 * B_HB, 5 * 4096);
#pragma unroll 1
        for (int c = 0; c < 5; c++) {
          if (c == 3) mbar_wait(bars + 8 * B_S3, 0);
          bulk_load(sb + off_ch(c) + U_BYTES, p.ssm_k + chan(b, c) * SEQ, 4096, bars + 8 * B_HB);
        }
#pragma unroll
        for (int c = 0; c < 4; c++) mbar_expect_tx(bars + 8 * (B_U + c), c < 3 ? U_BYTES : 2 * U_BYTES);
        mbar_wait(bars + 8 * B_USIG, 0);
        flag_wait(g_cnt + C_PREP + 32 * (b & 15), (epoch + 1) * NCTA);
        TS(23);
#pragma unroll
        for (int c = 0; c < 5; c++) {
          if (c == 3) mbar_wait(bars + 8 * (B_U + 2), 0);
          bulk_load(sb + off_ch(c), g_U + chan(b, c) * U_PITCH, U_BYTES, bars + 8 * (B_U + (c < 3 ? c : 3)));
          TSIF(c == 0 || c == 4, 116 + (c >> 2));
        }
      }
      epoch = __shfl_sync(0xffffffffu, epoch, 0);
      if (lane < 8) {
        const int src = (b & ~7) | step_src(hg, lane);
        mbar_wait(bars + 8 * B_ATTN, 0);
        TS(20);
        bool seen = false;
#pragma unroll 1
        for (int spins = 0; spins < SPIN_LIMIT; spins++) {
          const bool now = !seen && (int)(flag_read(g_cnt + C_O + 32 * src) - (epoch + 1)) >= 0;
          if (now && lane >= 1 && lane < 4) bulk_load(sb + off_o(lane), g_O + src * 1280, O_BYTES, bars + 8 * (B_FULL2 + lane));
          seen = seen || now;
          if (__all_sync(0xff, seen)) break;
        }
        TS(21);
        if (lane == 5) bulk_load(sb + OFF_GATE, g_gate + 128 * r, 512, bars + 8 * (B_FULL2 + 5));
#pragma unroll 1
        for (int j = 4; j < 8; j++) {
          if (lane == j) {
            mbar_wait(bars + 8 * (j < 6 ? B_C34 : B_EMPTY2 + j - 6), 0);
            bulk_load(sb + off_o(j), g_O + src * 1280, O_BYTES, bars + 8 * (B_FULL2 + j));
          }
          __syncwarp(0xff);
        }
        TS(22);
      }
    } else if (w == 2) {
      mbar_wait(bars + 8 * B_PREP, 0);
      flag_signal(g_cnt + C_PREP, 16, lane);
      TS(25);
      if (lane == 0) {
        mbar_arrive(bars + 8 * B_USIG);
        mbar_expect_tx(bars + 8 * B_ORB, (RB32 & 2 ? O_BYTES / 4 : O_BYTES) + 64);
        mbar_wait(bars + 8 * B_GATE, 0);
        publish(g_gate + 16 * b, sb + OFF_GATE + 64 * hg, 64, bars + 8 * B_ORB);
        mbar_wait(bars + 8 * B_ATTN, 0);
        if (RB32 & 2) {
          bulk_store(g_O + b * 1280, sb + OFF_OA, O_BYTES);
          bulk_wait_read();
          tma_2d(sb + OFF_KVX + 10240, &m.ol, 48, b * 160, bars + 8 * B_ORB);
        } else {
          publish(g_O + b * 1280, sb + OFF_OA, O_BYTES, bars + 8 * B_ORB);
        }
        TS(74);
        mbar_wait(bars + 8 * B_ORB, 0);
        flag_bump(g_cnt + C_O + 32 * b);
        TS(26);
        mbar_arrive(bars + 8 * B_OSIG);
        if (Y_SPLIT) {
          mbar_expect_tx(bars + 8 * B_YFULL, 20480);
          mbar_wait(bars + 8 * B_C34, 0);
          flag_wait(g_cnt + C_YE + 32 * hg, (lds32(sb + OFF_EPOCH) + 1) * 16);
          mbar_wait(bars + 8 * (B_EMPTY2 + 2), 0);
          tma_2d(sb + OFF_YT, &m.ye, 128 * r, 80 * hg, bars + 8 * B_YFULL);
          tma_2d(sb + OFF_YT + 10240, &m.ye, 128 * r + 64, 80 * hg, bars + 8 * B_YFULL);
        }
      }
    } else {
      if (lane == 0) {
        uint4* dst = g_WO + (hg * 8 + (r >> 1)) * 800 + (r & 1) * 80;
        mbar_wait(bars + 8 * B_S3, 0);
        asm volatile("cp.async.bulk.prefetch.L2.global [%0], 6400;" ::"l"(p.wo + b * 3200) : "memory");
        mbar_wait(bars + 8 * B_P1, 0);
        mbar_wait(bars + 8 * WB_TRIG, 0);
        mbar_expect_tx(bars + 8 * B_WST, WO_BYTES / 2);
        tma_3d(sb + OFF_WA, &m.wo, 0, 40 * r, 5 * hg, bars + 8 * B_WST);
        mbar_wait(bars + 8 * B_WST, 0);
#pragma unroll 1
        for (int n = 0; n < 5; n++) bulk_store(dst + 160 * n, sb + OFF_WA + 1280 * n, 1280);
        bulk_wait_read();
        mbar_expect_tx(bars + 8 * B_WST, WO_BYTES / 2);
#pragma unroll 1
        for (int n = 0; n < 5; n++) bulk_load(sb + OFF_WA + 1280 * n, dst + 160 * n, 1280, bars + 8 * B_WST);
        mbar_wait(bars + 8 * B_WST, 1);
        flag_bump(g_cnt + C_W + 32 * hg);
        mbar_arrive(bars + 8 * B_WOP);
        TS(71);
        mbar_expect_tx(bars + 8 * B_C34, 3 * (RB32 & 1 ? 1024 : U_BYTES));
        mbar_expect_tx(bars + 8 * B_YRB, 2 * (RB32 & 1 ? 1024 : U_BYTES));
#pragma unroll 1
        for (int c = 0; c < 5; c++) {
          if (Y_SPLIT && c == 3) {
            mbar_wait(bars + 8 * B_C34, 0);
            flag_bump(g_cnt + C_YE + 32 * (b >> 4));
          }
          mbar_wait(bars + 8 * (B_YST + c), 0);
          if (RB32 & 1) {
            bulk_store(g_U + chan(b, c) * U_PITCH, sb + off_ch(c), U_BYTES);
            bulk_wait_read();
            tma_2d(sb + off_ch(c), &m.yl, 48, chan(b, c) * (U_PITCH / 8), bars + 8 * (c < 3 ? B_C34 : B_YRB));
          } else {
            publish(g_U + chan(b, c) * U_PITCH, sb + off_ch(c), U_BYTES, bars + 8 * (c < 3 ? B_C34 : B_YRB));
          }
        }
        TS(75);
        mbar_wait(bars + 8 * B_C34, 0);
        mbar_wait(bars + 8 * B_YRB, 0);
        flag_bump(g_cnt + C_Y + 32 * (b >> 4));
        TS(27);
        mbar_arrive(bars + 8 * B_YSIG);
        if (!Y_SPLIT) mbar_expect_tx(bars + 8 * B_YFULL, 20480);
        flag_wait(g_cnt + C_Y + 32 * hg, (lds32(sb + OFF_EPOCH) + 1) * 16);
        TS(24);
        if (Y_SPLIT) mbar_wait(bars + 8 * (B_EMPTY2 + 2), 0);
        tma_2d(sb + OFF_YT + Y_SPLIT * 6144, &m.y, 128 * r, 80 * hg + Y_SPLIT * 48, bars + 8 * B_YFULL);
        tma_2d(sb + OFF_YT + Y_SPLIT * 6144 + 10240, &m.y, 128 * r + 64, 80 * hg + Y_SPLIT * 48, bars + 8 * B_YFULL);
      }
    }
  } else {
    asm volatile("setmaxnreg.inc.sync.aligned.u32 152;");
    if (wg < 2) {
      float acc[120];
#pragma unroll
      for (int i = 0; i < 120; i++) acc[i] = 0.f;
      const uint32_t da = desc_lo(sb + wg * 8192, 16), db = desc_lo(sb + ST_W, 8192), dc = desc_lo(sb + ST_WT, 2048);
      mbar_wait(bars + 8 * B_F0, 0);
      TSIF(w == 0 && wg == 0, 1);
      wg_fence();
#pragma unroll
      for (int k = 0; k < 4; k++) WgSST<192>::mma<HI_SW128, HI_SW128>(acc, da + 2 * k, db + 128 * k, 1);
      wg_commit();
      mbar_wait(bars + 8 * B_FULL1, 0);
      wg_fence();
#pragma unroll
      for (int k = 0; k < 4; k++) WgSST<48>::mma<HI_SW128, HI_SW32>(acc + 96, da + 2 * k, dc + 32 * k, 1);
      wg_commit();
#pragma unroll 1
      for (int kb = 1; kb < 10; kb++) {
        mbar_wait(bars + 8 * (B_FULL1 + (kb & 3)), (kb >> 2) & 1);
        const uint32_t so = (kb & 3) * (STAGE_BYTES >> 4);
        wg_fence();
#pragma unroll
        for (int k = 0; k < 4; k++) {
          WgSST<192>::mma<HI_SW128, HI_SW128>(acc, da + so + 2 * k, db + so + 128 * k, 1);
          WgSST<48>::mma<HI_SW128, HI_SW32>(acc + 96, da + so + 2 * k, dc + so + 32 * k, 1);
        }
        wg_commit();
        wg_wait<1>();
        if (lane == 0) mbar_arrive(bars + 8 * (kb == 4 ? B_E3 : B_EMPTY1 + ((kb - 1) & 3)));
      }
      mbar_wait(bars + 8 * B_EPOCH, 0);
      const uint32_t tag = lds32(sb + OFF_EPOCH) + 1;
      mbar_wait(bars + 8 * B_S3, 0);
      wg_wait<0>();
      pin<120>(acc);
      if (lane == 0) mbar_arrive(bars + 8 * B_P1);
      TSM(w == 0, 3 + wg);
      attention(acc, sb, b, wg, w, lane, tag);
    } else {
      const int tw = tid & 127, chl = 64 * (b & 1) + 8 * w + (lane >> 2);
      uint4* up = g_U + chl * U_PITCH + ((4 * (b >> 1) + (lane & 3)) ^ ((b >> 2) & 1));
      uint2 sw[10];
      uint32_t dv = 0;
      if (lane < 5) dv = __ldg(reinterpret_cast<const unsigned short*>(p.ssm_D) + chan(b, lane));
#pragma unroll
      for (int i = 0; i < 10; i++) sw[i] = ldg64(reinterpret_cast<const uint2*>(p.shift_k) + chl + 128 * (i >> 1) + 32 * (i & 1));
      uint32_t tab[12];
      uint32_t tt[2];
      fft_tables(tab, tw);
      fft_twiddles(tt, tw);
      uint4 res[10];
#pragma unroll
      for (int i = 0; i < 10; i++) res[i] = make_uint4(0, 0, 0, 0);
#pragma unroll 1
      for (int slab = 0; slab < 5; slab++) {
#pragma unroll
        for (int i = 0; i < 8; i++) res[i] = res[i + 2];
        prep_slab(res + 8, sw, sb, slab, w, lane);
        TSIF(w == 0, 99 + 4 * slab);
#pragma unroll
        for (int i = 0; i < 8; i++) sw[i] = sw[i + 2];
      }
      TSIF(w == 0, 28);
      __syncwarp();
      if (lane == 0) mbar_arrive(bars + 8 * B_KVD + ((res[8].x ^ res[9].x) & p.zero));
      mbar_wait(bars + 8 * B_KVD, 0);
      fft_tables_store(tab, sb, tw);
      mbar_wait(bars + 8 * B_LAST, 0);
#pragma unroll
      for (int i = 0; i < 10; i++) up[(128 * (i >> 1) + 32 * (i & 1)) * U_PITCH] = res[i];
      __syncwarp();
      if (lane == 0) mbar_arrive(bars + 8 * B_PREP);
      TSIF(w == 0, 5);
      mbar_wait(bars + 8 * B_LAST, 0);
      prep_gate(p, sb, b, w, lane);
      __syncwarp();
      if (lane == 0) mbar_arrive(bars + 8 * B_GATE);
      TSIF(w == 0, 72);
      mbar_wait(bars + 8 * B_HB, 0);
      TSIF(w == 0, 2);
      const uint32_t ha = sb + U_BYTES + ((tw >> 3) * 16 + 8 + (tw & 7)) * 16;
      uint4 hv[5];
#pragma unroll
      for (int c = 0; c < 5; c++) hv[c] = lds128(ha + off_ch(c));
      __syncwarp();
#pragma unroll
      for (int c = 0; c < 5; c++) sts128((ha ^ 16) + off_ch(c), hv[c].x, hv[c].y, hv[c].z, hv[c].w);
      asm volatile("st.shared.v2.u32 [%0], {%1, %2};" ::"r"(sb + OFF_TT + 8 * tw), "r"(tt[0]), "r"(tt[1]) : "memory");
      if (tw < 5) asm volatile("st.shared.f32 [%0], %1;" ::"r"(sb + OFF_D + 4 * tw), "f"(bf_lo(dv) * 0.125f) : "memory");
      fence_async_smem();
      __syncwarp();
      if (lane == 0) mbar_arrive(bars + 8 * B_HA);
      TSIF(w == 0, 6);
    }

    FftConst fc;
    TSM(w == 0 && wg == 0, 104);
    mbar_wait(bars + 8 * B_HA, 0);
    fft_matrices(fc, sb, w, lane);
    TSM(w == 0 && wg == 0, 105);
    TSM(w == 0 && wg == 2, 124);
#pragma unroll 1
    for (uint32_t tasks = wg == 0 ? TASK0 : wg == 1 ? TASK1 : TASK2; tasks; tasks >>= 4) {
      const int c = (tasks & 7) - 1;
      conv_channel(fc, sb, c, wg, w, lane);
      if (lane == 0) mbar_arrive(bars + 8 * (B_YST + c));
      TSM(w == 0, 10 + c);
    }

    if (wg != WO_SKIP) {
      const int wg = (warp >> 2) > WO_SKIP ? (warp >> 2) - 1 : warp >> 2;
      const int g = lane >> 2;
      float acc[40];
#pragma unroll
      for (int i = 0; i < 40; i++) acc[i] = 0.f;
      const uint32_t da = desc_lo(sb + wg * 1024, 2048), db = desc_lo(sb, 2560);
      mbar_wait(bars + 8 * B_ORB, 0);
      mbar_wait(bars + 8 * B_FULL2, 0);
      TSM(w == 0, 15 + wg);
#pragma unroll 1
      for (int j = 0; j < 8; j++) {
        if (j == (wg ? WO_E1 : WO_E0)) mbar_wait(bars + 8 * B_CVD, 0);
        mbar_wait(bars + 8 * (B_FULL2 + j), 0);
        TSM(w == 0 && wg == 0, 44 + (j < 4 ? j : j + 6));
        const uint32_t oa = da + (off_o(j) >> 4), ob = db + (off_w(j) >> 4);
        wg_fence();
#pragma unroll
        for (int k = 0; k < 5; k++) WgSST<80>::mma<HI_NONE, HI_SW32>(acc, oa + 256 * k, ob + 32 * k, 1);
        wg_commit();
        wg_wait<1>();
        if (j >= 1 && j <= 4 && lane == 0) mbar_arrive(bars + 8 * (B_EMPTY2 + j - 1));
      }
      TSIF(w == 0 && wg == 0, 113);
      const int tr = 64 * wg + 16 * w + (lane & 15);
      const uint32_t fm = sb + OFF_QS + tr * 128, fx = (lane >> 4) ^ (tr & 7);
      const uint32_t ft = sb + OFF_QT + tr * 32 + (((lane >> 4) ^ (tr >> 2)) & 1) * 16;
      const float g0 = __uint_as_float(lds32(sb + OFF_GATE + (64 * wg + 16 * w + g) * 4));
      const float g1 = __uint_as_float(lds32(sb + OFF_GATE + (64 * wg + 16 * w + 8 + g) * 4));
      const uint32_t ga = pack2(g0, g0), gb = pack2(g1, g1);
      const uint32_t na = pack2(1.f - g0, 1.f - g0), nb = pack2(1.f - g1, 1.f - g1);

      uint32_t qf[20];
      mbar_wait(bars + 8 * B_QF, 0);
      TSM(w == 0 && wg == 0, 99);
#pragma unroll
      for (int j = 0; j < 5; j++) ldsm4(qf + 4 * j, j < 4 ? fm + ((fx ^ (2 * j)) << 4) : ft);
#pragma unroll
      for (int i = 0; i < 20; i++) {
        qf[i] = bmul((i & 1) ? gb : ga, qf[i]);
        asm volatile("" : "+r"(qf[i]));
      }

      wg_wait<0>();
      pin<40>(acc);
      TSM(w == 0, 17 + wg);
      uint32_t pb[20];
#pragma unroll
      for (int j = 0; j < 10; j++) {
        pb[2 * j] = bmul(na, pack2(acc[4 * j], acc[4 * j + 1]));
        pb[2 * j + 1] = bmul(nb, pack2(acc[4 * j + 2], acc[4 * j + 3]));
        asm volatile("" : "+r"(pb[2 * j]), "+r"(pb[2 * j + 1]));
      }
      const uint32_t ya = sb + OFF_YT + wg * 10240 + ((lane >> 4) * 8 + (lane & 7)) * 128 +
                          (((2 * w + (((lane >> 3) & 1) ^ wg)) ^ (lane & 7)) << 4);
      mbar_wait(bars + 8 * B_YFULL, 0);
      TSM(w == 0 && wg == 0, 19);
#pragma unroll
      for (int j = 0; j < 5; j++) {
        uint32_t y[4];
        ldsm4t(y, ya + 2048 * j);
#pragma unroll
        for (int i = 0; i < 4; i++)
          qf[4 * j + i] = bfma(qf[4 * j + i], y[i], pb[4 * j + i]);
      }
#pragma unroll
      for (int j = 0; j < 5; j++) stsm4(j < 4 ? fm + ((fx ^ (2 * j)) << 4) : ft, qf + 4 * j);
      fence_async_smem();
      __syncwarp();
      if (lane == 0) {
        const int row = 64 * wg + 16 * w;
        asm volatile("cp.async.bulk.tensor.2d.global.shared::cta.bulk_group [%0, {%2, %3}], [%1];"
                     ::"l"(&m.om), "r"(sb + OFF_QS + row * 128), "r"(80 * hg), "r"(128 * r + row) : "memory");
        asm volatile("cp.async.bulk.tensor.2d.global.shared::cta.bulk_group [%0, {%2, %3}], [%1];"
                     ::"l"(&m.ot), "r"(sb + OFF_QT + row * 32), "r"(80 * hg + 64), "r"(128 * r + row) : "memory");
        asm volatile("cp.async.bulk.commit_group;\ncp.async.bulk.wait_group.read 0;" ::: "memory");
      }
      TSM(w == 0 || w == 3, 40 + 2 * wg + (w & 1));
    }
  }
}

typedef CUresult (*EncodeFn)(CUtensorMap*, CUtensorMapDataType, cuuint32_t, void*, const cuuint64_t*, const cuuint64_t*,
                             const cuuint32_t*, const cuuint32_t*, CUtensorMapInterleave, CUtensorMapSwizzle,
                             CUtensorMapL2promotion, CUtensorMapFloatOOBfill);

void encode(EncodeFn fn, CUtensorMap* tm, const void* base, int rank, const cuuint64_t* dims, const cuuint64_t* strides,
            const cuuint32_t* box, CUtensorMapSwizzle swz) {
  const cuuint32_t ones[3] = {1, 1, 1};
  fn(tm, CU_TENSOR_MAP_DATA_TYPE_BFLOAT16, rank, const_cast<void*>(base), dims, strides, box, ones,
     CU_TENSOR_MAP_INTERLEAVE_NONE, swz, CU_TENSOR_MAP_L2_PROMOTION_L2_128B, CU_TENSOR_MAP_FLOAT_OOB_FILL_NONE);
}

}

extern "C" void kernel_launch(void* const* d_in, const int* in_sizes, int n_in, void* d_out, int out_size) {
  (void)in_sizes; (void)n_in; (void)out_size;
  Params p;
  p.q = (const __nv_bfloat16*)d_in[0];
  p.k = (const __nv_bfloat16*)d_in[1];
  p.v = (const __nv_bfloat16*)d_in[2];
  p.shift_k = (const __nv_bfloat16*)d_in[3];
  p.ssm_k = (const __nv_bfloat16*)d_in[4];
  p.ssm_D = (const __nv_bfloat16*)d_in[5];
  p.wqkv = (const __nv_bfloat16*)d_in[7];
  p.wo = (const __nv_bfloat16*)d_in[8];
  p.gate_w = (const __nv_bfloat16*)d_in[9];
  p.out = (__nv_bfloat16*)d_out;
  p.zero = 0;

  static EncodeFn fn = nullptr;
  static void *yaddr = nullptr, *oaddr = nullptr;
  if (!fn) {
    cudaDriverEntryPointQueryResult qr;
    void* f = nullptr;
    cudaGetDriverEntryPoint("cuTensorMapEncodeTiled", &f, cudaEnableDefault, &qr);
    fn = (EncodeFn)f;
    cudaGetSymbolAddress(&yaddr, g_U);
    cudaGetSymbolAddress(&oaddr, g_O);
    cudaFuncSetAttribute(fused_kernel, cudaFuncAttributeMaxDynamicSharedMemorySize, SMEM_BYTES);
  }
  Maps m;
  {
    const cuuint64_t dims[3] = {640, 1024, 2}, st[2] = {2560, 1280};
    const cuuint32_t box[3] = {64, 64, 2};
    encode(fn, &m.x, p.q, 3, dims, st, box, CU_TENSOR_MAP_SWIZZLE_128B);
  }
  {
    const cuuint64_t dims[3] = {640, 640, 3}, st[2] = {3840, 1280};
    const cuuint32_t box[3] = {64, 64, 3}, boxt[3] = {16, 64, 3};
    encode(fn, &m.wm, p.wqkv, 3, dims, st, box, CU_TENSOR_MAP_SWIZZLE_128B);
    encode(fn, &m.wt, p.wqkv, 3, dims, st, boxt, CU_TENSOR_MAP_SWIZZLE_32B);
  }
  {
    const cuuint64_t dims[3] = {64, 2048, 10}, st[2] = {1280, 128};
    const cuuint32_t boxk[3] = {64, 35, 1}, boxv[3] = {64, 32, 1};
    encode(fn, &m.k, p.k, 3, dims, st, boxk, CU_TENSOR_MAP_SWIZZLE_128B);
    encode(fn, &m.v, p.v, 3, dims, st, boxv, CU_TENSOR_MAP_SWIZZLE_128B);
  }
  {
    const cuuint64_t dims[3] = {16, 640, 40}, st[2] = {1280, 32};
    const cuuint32_t box[3] = {16, 40, 5};
    encode(fn, &m.wo, p.wo, 3, dims, st, box, CU_TENSOR_MAP_SWIZZLE_32B);
  }
  {
    const cuuint64_t dims[2] = {2048, 640}, st[1] = {U_PITCH * 16};
    const cuuint32_t box[2] = {64, Y_SPLIT ? 32 : 80}, boxe[2] = {64, 48};
    encode(fn, &m.ye, yaddr, 2, dims, st, boxe, CU_TENSOR_MAP_SWIZZLE_128B);
    encode(fn, &m.y, yaddr, 2, dims, st, box, CU_TENSOR_MAP_SWIZZLE_128B);
    const cuuint64_t dl[2] = {64, DIM * U_PITCH / 8}, dol[2] = {64, NCTA * 160}, sl[1] = {128};
    const cuuint32_t bl[2] = {16, 32}, bol[2] = {16, 160};
    encode(fn, &m.yl, yaddr, 2, dl, sl, bl, CU_TENSOR_MAP_SWIZZLE_NONE);
    encode(fn, &m.ol, oaddr, 2, dol, sl, bol, CU_TENSOR_MAP_SWIZZLE_NONE);
  }
  {
    const cuuint64_t dims[2] = {640, 2048}, st[1] = {1280};
    const cuuint32_t bqm[2] = {64, 128}, bqt[2] = {16, 128}, bom[2] = {64, 16}, bot[2] = {16, 16};
    encode(fn, &m.qm, p.q, 2, dims, st, bqm, CU_TENSOR_MAP_SWIZZLE_128B);
    encode(fn, &m.qt, p.q, 2, dims, st, bqt, CU_TENSOR_MAP_SWIZZLE_32B);
    encode(fn, &m.om, p.out, 2, dims, st, bom, CU_TENSOR_MAP_SWIZZLE_128B);
    encode(fn, &m.ot, p.out, 2, dims, st, bot, CU_TENSOR_MAP_SWIZZLE_32B);
  }
  fused_kernel<<<NCTA, NTHR, SMEM_BYTES>>>(m, p);
}
```

```cpp
#include <cuda.h>
#include <cuda_bf16.h>
#include <cuda_runtime.h>
#include <stdint.h>

namespace {

constexpr int SEQ = 2048, DIM = 640, NCTA = 128, NTHR = 512;

#define TRIG_KB 9
#define KV_KB 2
#define DEV_EXIT 0
#define FENCE_LO 0
#define FENCE_HI 0
#define WB_TRIG B_USIG
#define T_ISSUE 256
#define RB32 3
#define WO_SKIP 1
#define WO_E0 1
#define WO_E1 0
#define HR_AT 4
#define HALO_INIT B_E3
#define T_INIT 448
#define TASK0 0x3
#define TASK1 0x52
#define TASK2 0x41
#define WL_TRIG B_WOP

constexpr uint32_t STAGE_BYTES = 47104, ST_W = 16384, ST_WT = 40960;
constexpr uint32_t O_BYTES = 20480, WO_BYTES = 12800;
constexpr uint32_t OFF_OA = 0;
constexpr uint32_t OFF_QS = 3 * O_BYTES, OFF_QT = OFF_QS + 16384;
constexpr uint32_t OFF_WC = 81920;
constexpr uint32_t OFF_WA = 94720;
constexpr uint32_t OFF_GATE = 145920;
constexpr uint32_t OFF_TT = 146432;
constexpr uint32_t OFF_KVX = 148480;
constexpr uint32_t OFF_CH3 = 163840;
constexpr uint32_t CH_BYTES = 12288, U_BYTES = 4096;
constexpr uint32_t OFF_FT = 225280, OFF_GT = 229376;
constexpr uint32_t OFF_CH0 = 188416;
constexpr uint32_t OFF_KVS = OFF_CH0, KVS_V = 4480, KVS_BYTES = 8576;
constexpr uint32_t OFF_YT = 163840;
constexpr uint32_t OFF_BAR = 231936;
constexpr uint32_t SMEM_BYTES = OFF_BAR + 512;

enum : uint32_t {
  B_EMPTY1 = 0, B_S3 = 3, B_E3 = 4, B_EMPTY2 = 5, B_ATTN = 9, B_P1 = 10,
  B_GATE = 11, B_HA = 12, B_KVD = 13, B_PREP = 14, B_YST = 15,
  B_CVD = 20,
  B_FULL2 = 21, B_U = 29, B_KV = 33, B_HB = 38, B_C34 = 39, B_YRB = 40, B_YFULL = 41, B_EPOCH = 42, B_LAST = 43, B_OSIG = 44,
  B_WOP = 45, B_USIG = 46, B_WST = 47, B_QF = 48, B_ORB = 49, B_YSIG = 50,
  B_F0 = 51, B_FULL1 = 52
};
constexpr uint32_t OFF_EPOCH = OFF_BAR + 8 * 58, OFF_D = OFF_BAR + 8 * 60;
__device__ __forceinline__ uint32_t off_o(int j) { return j < 4 ? OFF_OA + j * O_BYTES : j < 6 ? OFF_CH0 + (j - 4) * O_BYTES : OFF_OA + (j - 6) * O_BYTES; }
__device__ __forceinline__ uint32_t off_w(int j) { return j < 4 ? OFF_WA + j * WO_BYTES : j == 4 ? OFF_KVX : j == 5 ? OFF_WC : OFF_WA + (j - 6) * WO_BYTES; }
__device__ __forceinline__ int step_src(int hg, int j) { return j == 0 ? hg : j <= hg ? j - 1 : j; }
__device__ __forceinline__ bool tail_first(int hg) { return (hg & 3) == 3; }
__device__ __forceinline__ uint32_t off_ch(int c) { return (c < 3 ? OFF_CH0 : OFF_CH3 - 3 * CH_BYTES) + c * CH_BYTES; }

#define U_PITCH 264
__device__ __align__(1024) uint4 g_U[DIM * U_PITCH];
__device__ __align__(128) uint4 g_O[NCTA * 1280];
__device__ uint4 g_WO[64 * 800];
__device__ uint4 g_halo[NCTA * 2 * 7 * 32];
__device__ __align__(128) float g_gate[SEQ];
__device__ unsigned g_cnt[32 * (1 + 2 * 16 + 8 + NCTA)];
constexpr int C_LAUNCH = 0, C_PREP = 32, C_Y = 32 * 17, C_W = 32 * 33, C_O = 32 * 41;

#define TSM(cond, slot) do { } while (0)
#define TSIF(cond, slot) do { if (__LINE__ >= FENCE_LO && __LINE__ < FENCE_HI) sched_fence(); } while (0)
__device__ __forceinline__ void sched_fence() {
  asm volatile("{\n.reg .pred p;\n.reg .u32 c;\nmov.u32 c, %%clock;\nsetp.eq.u32 p, c, 0;\n@p st.shared.u32 [%0], c;\n}"
               ::"r"(1024 + OFF_EPOCH + 4) : "memory");
}
#define TS(slot) TSIF(true, slot)

struct Params {
  const __nv_bfloat16 *q, *k, *v, *shift_k, *ssm_k, *ssm_D, *wqkv, *wo, *gate_w;
  __nv_bfloat16* out;
  uint32_t zero;
};

constexpr int SPIN_LIMIT = 1 << 17;

__device__ __forceinline__ void mbar_init(uint32_t bar, uint32_t count) {
  asm volatile("mbarrier.init.shared::cta.b64 [%0], %1;" ::"r"(bar), "r"(count) : "memory");
}
__device__ __forceinline__ void mbar_expect_tx(uint32_t bar, uint32_t bytes) {
  asm volatile("mbarrier.arrive.expect_tx.shared::cta.b64 _, [%0], %1;" ::"r"(bar), "r"(bytes) : "memory");
}
__device__ __forceinline__ void mbar_arrive(uint32_t bar) {
  asm volatile("mbarrier.arrive.shared::cta.b64 _, [%0];" ::"r"(bar) : "memory");
}
__device__ __forceinline__ void mbar_wait(uint32_t bar, uint32_t parity) {
  uint32_t ok;
  int spins = 0;
  do {
      asm volatile("{\n.reg .pred p;\nmbarrier.try_wait.parity.shared::cta.b64 p, [%1], %2;\nselp.b32 %0, 1, 0, p;\n}"
                   : "=r"(ok) : "r"(bar), "r"(parity) : "memory");
    if (++spins > SPIN_LIMIT) break;
  } while (!ok);
}
__device__ __forceinline__ unsigned flag_read(const unsigned* p) {
  unsigned v;
  asm volatile("ld.relaxed.gpu.global.u32 %0, [%1];" : "=r"(v) : "l"(p) : "memory");
  return v;
}
__device__ __forceinline__ void flag_poll(const unsigned* p, unsigned target) {
  unsigned v;
  int spins = 0;
  do {
    asm volatile("ld.relaxed.gpu.global.u32 %0, [%1];" : "=r"(v) : "l"(p) : "memory");
    if (++spins > SPIN_LIMIT) break;
  } while ((int)(v - target) < 0);
}
__device__ __forceinline__ void flag_wait(const unsigned* p, unsigned target) {
  flag_poll(p, target);
}
__device__ __forceinline__ void flag_signal(unsigned* p, int n, int lane) {
  if (lane == 0) asm volatile("fence.release.gpu;" ::: "memory");
  __syncwarp();
  if (lane < n) asm volatile("red.relaxed.gpu.global.add.u32 [%0], 1;" ::"l"(p + 32 * lane) : "memory");
}
__device__ __forceinline__ void flag_bump(unsigned* p) {
  asm volatile("red.relaxed.gpu.global.add.u32 [%0], 1;" ::"l"(p) : "memory");
}
__device__ __forceinline__ void fence_async_smem() { asm volatile("fence.proxy.async.shared::cta;" ::: "memory"); }
__device__ __forceinline__ void wg_sync(int id) { asm volatile("bar.sync %0, 128;" ::"r"(id) : "memory"); }

__device__ __forceinline__ void tma_2d(uint32_t dst, const CUtensorMap* tm, int c0, int c1, uint32_t bar) {
  asm volatile("cp.async.bulk.tensor.2d.shared::cluster.global.mbarrier::complete_tx::bytes [%0], [%1, {%3, %4}], [%2];"
               ::"r"(dst), "l"(tm), "r"(bar), "r"(c0), "r"(c1) : "memory");
}
__device__ __forceinline__ void tma_3d(uint32_t dst, const CUtensorMap* tm, int c0, int c1, int c2, uint32_t bar) {
  asm volatile("cp.async.bulk.tensor.3d.shared::cluster.global.mbarrier::complete_tx::bytes [%0], [%1, {%3, %4, %5}], [%2];"
               ::"r"(dst), "l"(tm), "r"(bar), "r"(c0), "r"(c1), "r"(c2) : "memory");
}
__device__ __forceinline__ void bulk_load(uint32_t dst, const void* src, uint32_t bytes, uint32_t bar) {
  asm volatile("cp.async.bulk.shared::cluster.global.mbarrier::complete_tx::bytes [%0], [%1], %2, [%3];"
               ::"r"(dst), "l"(src), "r"(bytes), "r"(bar) : "memory");
}
__device__ __forceinline__ void bulk_store(void* dst, uint32_t src, uint32_t bytes) {
  asm volatile("cp.async.bulk.global.shared::cta.bulk_group [%0], [%1], %2;" ::"l"(dst), "r"(src), "r"(bytes) : "memory");
}
__device__ __forceinline__ void bulk_wait_read() {
  asm volatile("cp.async.bulk.commit_group;\ncp.async.bulk.wait_group.read 0;" ::: "memory");
}

__device__ __forceinline__ void publish(void* dst, uint32_t src, uint32_t bytes, uint32_t bar) {
  bulk_store(dst, src, bytes);
  bulk_wait_read();
  bulk_load(src, dst, bytes, bar);
}

__device__ __forceinline__ void wg_fence() { asm volatile("wgmma.fence.sync.aligned;" ::: "memory"); }
__device__ __forceinline__ void wg_commit() { asm volatile("wgmma.commit_group.sync.aligned;" ::: "memory"); }
template <int N> __device__ __forceinline__ void wg_wait() { asm volatile("wgmma.wait_group.sync.aligned %0;" ::"n"(N) : "memory"); }
__device__ __forceinline__ uint32_t desc_lo(uint32_t addr, uint32_t lbo) { return ((addr & 0x3FFFF) >> 4) | ((lbo >> 4) << 16); }
constexpr uint32_t desc_hi(uint32_t sbo, uint32_t swz) { return (sbo >> 4) | (swz << 30); }
constexpr uint32_t HI_SW128 = desc_hi(1024, 1), HI_SW64 = desc_hi(512, 2), HI_SW32 = desc_hi(256, 3), HI_NONE = desc_hi(128, 0);
template <int N> __device__ __forceinline__ void pin(float* d) {
#pragma unroll
  for (int i = 0; i < N; i++) asm volatile("" : "+f"(d[i])::"memory");
}

__device__ __forceinline__ uint32_t lds32(uint32_t a) {
  uint32_t v;
  asm volatile("ld.volatile.shared.u32 %0, [%1];" : "=r"(v) : "r"(a) : "memory");
  return v;
}
__device__ __forceinline__ uint2 ldg64(const void* a) {
  uint2 v;
  asm volatile("ld.global.nc.v2.u32 {%0, %1}, [%2];" : "=r"(v.x), "=r"(v.y) : "l"(a) : "memory");
  return v;
}
__device__ __forceinline__ void ldsm4(uint32_t* r, uint32_t a) {
  asm volatile("ldmatrix.sync.aligned.m8n8.x4.shared.b16 {%0, %1, %2, %3}, [%4];"
               : "=r"(r[0]), "=r"(r[1]), "=r"(r[2]), "=r"(r[3]) : "r"(a) : "memory");
}
__device__ __forceinline__ void ldsm4t(uint32_t* r, uint32_t a) {
  asm volatile("ldmatrix.sync.aligned.m8n8.x4.trans.shared.b16 {%0, %1, %2, %3}, [%4];"
               : "=r"(r[0]), "=r"(r[1]), "=r"(r[2]), "=r"(r[3]) : "r"(a) : "memory");
}
__device__ __forceinline__ uint2 lds64(uint32_t a) {
  uint2 v;
  asm volatile("ld.shared.v2.u32 {%0, %1}, [%2];" : "=r"(v.x), "=r"(v.y) : "r"(a) : "memory");
  return v;
}
__device__ __forceinline__ uint4 lds128(uint32_t a) {
  uint4 v;
  asm volatile("ld.shared.v4.u32 {%0, %1, %2, %3}, [%4];" : "=r"(v.x), "=r"(v.y), "=r"(v.z), "=r"(v.w) : "r"(a) : "memory");
  return v;
}
__device__ __forceinline__ void sts128(uint32_t a, uint32_t x, uint32_t y, uint32_t z, uint32_t w) {
  asm volatile("st.shared.v4.u32 [%0], {%1, %2, %3, %4};" ::"r"(a), "r"(x), "r"(y), "r"(z), "r"(w) : "memory");
}
__device__ __forceinline__ void stsm4(uint32_t a, const uint32_t* r) {
  asm volatile("stmatrix.sync.aligned.m8n8.x4.shared.b16 [%0], {%1, %2, %3, %4};" ::"r"(a), "r"(r[0]), "r"(r[1]), "r"(r[2]), "r"(r[3]) : "memory");
}
__device__ __forceinline__ uint32_t pack2(float lo, float hi) {
  uint32_t r;
  asm("cvt.rn.bf16x2.f32 %0, %1, %2;" : "=r"(r) : "f"(hi), "f"(lo));
  return r;
}
__device__ __forceinline__ uint32_t movm(uint32_t a) {
  uint32_t d;
  asm volatile("movmatrix.sync.aligned.m8n8.trans.b16 %0, %1;" : "=r"(d) : "r"(a));
  return d;
}
__device__ __forceinline__ uint32_t bmul(uint32_t a, uint32_t b) {
  uint32_t d;
  asm("mul.rn.bf16x2 %0, %1, %2;" : "=r"(d) : "r"(a), "r"(b));
  return d;
}
__device__ __forceinline__ uint32_t badd(uint32_t a, uint32_t b) {
  uint32_t d;
  asm("add.rn.bf16x2 %0, %1, %2;" : "=r"(d) : "r"(a), "r"(b));
  return d;
}
__device__ __forceinline__ uint32_t bfma(uint32_t a, uint32_t b, uint32_t c) {
  uint32_t d;
  asm("fma.rn.bf16x2 %0, %1, %2, %3;" : "=r"(d) : "r"(a), "r"(b), "r"(c));
  return d;
}
__device__ __forceinline__ float bf_lo(uint32_t x) { return __uint_as_float(x << 16); }
__device__ __forceinline__ float bf_hi(uint32_t x) { return __uint_as_float(x & 0xFFFF0000u); }
__device__ __forceinline__ float ex2(float x) {
  float y;
  asm("ex2.approx.ftz.f32 %0, %1;" : "=f"(y) : "f"(x));
  return y;
}
__device__ __forceinline__ float rcp(float x) {
  float y;
  asm("rcp.approx.ftz.f32 %0, %1;" : "=f"(y) : "f"(x));
  return y;
}
__device__ __forceinline__ void mma16816(float* d, uint32_t a0, uint32_t a1, uint32_t a2, uint32_t a3, uint32_t b0, uint32_t b1) {
  asm volatile("mma.sync.aligned.m16n8k16.row.col.f32.bf16.bf16.f32 {%0, %1, %2, %3}, {%4, %5, %6, %7}, {%8, %9}, {%0, %1, %2, %3};"
               : "+f"(d[0]), "+f"(d[1]), "+f"(d[2]), "+f"(d[3])
               : "r"(a0), "r"(a1), "r"(a2), "r"(a3), "r"(b0), "r"(b1));
}
__device__ __forceinline__ void mma1688(float* d, uint32_t a0, uint32_t a1, uint32_t b0) {
  asm volatile("mma.sync.aligned.m16n8k8.row.col.f32.bf16.bf16.f32 {%0, %1, %2, %3}, {%4, %5}, {%6}, {%0, %1, %2, %3};"
               : "+f"(d[0]), "+f"(d[1]), "+f"(d[2]), "+f"(d[3])
               : "r"(a0), "r"(a1), "r"(b0));
}

template <int N> struct WgRS;
template <int N> struct WgSST;
template <> struct WgRS<32> {
  template <uint32_t HB>
  static __device__ __forceinline__ void mma(float* d, const uint32_t* a, uint32_t db) {
    asm volatile("{\n.reg .pred p;\n.reg .b64 db;\nsetp.ne.b32 p, %22, 0;\n"
      "mov.b64 db, {%20, %21};\n"
      "wgmma.mma_async.sync.aligned.m64n32k16.f32.bf16.bf16 {"
      "%0, %1, %2, %3, %4, %5, %6, %7, %8, %9, %10, %11, %12, %13, %14, %15"
      "}, {%16, %17, %18, %19}, db, p, 1, 1, 1;\n}\n"
      : "+f"(d[0]), "+f"(d[1]), "+f"(d[2]), "+f"(d[3]), "+f"(d[4]), "+f"(d[5]), "+f"(d[6]), "+f"(d[7]),
        "+f"(d[8]), "+f"(d[9]), "+f"(d[10]), "+f"(d[11]), "+f"(d[12]), "+f"(d[13]), "+f"(d[14]), "+f"(d[15])
      : "r"(a[0]), "r"(a[1]), "r"(a[2]), "r"(a[3]), "r"(db), "n"(HB), "n"(1));
  }
  template <uint32_t HB>
  static __device__ __forceinline__ void set(float* d, const uint32_t* a, uint32_t db) {
    asm volatile("{\n.reg .pred p;\n.reg .b64 db;\nsetp.ne.b32 p, %22, 0;\n"
      "mov.b64 db, {%20, %21};\n"
      "wgmma.mma_async.sync.aligned.m64n32k16.f32.bf16.bf16 {"
      "%0, %1, %2, %3, %4, %5, %6, %7, %8, %9, %10, %11, %12, %13, %14, %15"
      "}, {%16, %17, %18, %19}, db, p, 1, 1, 1;\n}\n"
      : "=f"(d[0]), "=f"(d[1]), "=f"(d[2]), "=f"(d[3]), "=f"(d[4]), "=f"(d[5]), "=f"(d[6]), "=f"(d[7]),
        "=f"(d[8]), "=f"(d[9]), "=f"(d[10]), "=f"(d[11]), "=f"(d[12]), "=f"(d[13]), "=f"(d[14]), "=f"(d[15])
      : "r"(a[0]), "r"(a[1]), "r"(a[2]), "r"(a[3]), "r"(db), "n"(HB), "n"(0));
  }
};
template <> struct WgRS<64> {
  template <uint32_t HB>
  static __device__ __forceinline__ void mma(float* d, const uint32_t* a, uint32_t db) {
    asm volatile("{\n.reg .pred p;\n.reg .b64 db;\nsetp.ne.b32 p, %38, 0;\n"
      "mov.b64 db, {%36, %37};\n"
      "wgmma.mma_async.sync.aligned.m64n64k16.f32.bf16.bf16 {"
      "%0, %1, %2, %3, %4, %5, %6, %7, %8, %9, %10, %11, %12, %13, %14, %15, "
      "%16, %17, %18, %19, %20, %21, %22, %23, %24, %25, %26, %27, %28, %29, %30, %31"
      "}, {%32, %33, %34, %35}, db, p, 1, 1, 1;\n}\n"
      : "+f"(d[0]), "+f"(d[1]), "+f"(d[2]), "+f"(d[3]), "+f"(d[4]), "+f"(d[5]), "+f"(d[6]), "+f"(d[7]),
        "+f"(d[8]), "+f"(d[9]), "+f"(d[10]), "+f"(d[11]), "+f"(d[12]), "+f"(d[13]), "+f"(d[14]), "+f"(d[15]),
        "+f"(d[16]), "+f"(d[17]), "+f"(d[18]), "+f"(d[19]), "+f"(d[20]), "+f"(d[21]), "+f"(d[22]), "+f"(d[23]),
        "+f"(d[24]), "+f"(d[25]), "+f"(d[26]), "+f"(d[27]), "+f"(d[28]), "+f"(d[29]), "+f"(d[30]), "+f"(d[31])
      : "r"(a[0]), "r"(a[1]), "r"(a[2]), "r"(a[3]), "r"(db), "n"(HB), "n"(1));
  }
  template <uint32_t HB>
  static __device__ __forceinline__ void set(float* d, const uint32_t* a, uint32_t db) {
    asm volatile("{\n.reg .pred p;\n.reg .b64 db;\nsetp.ne.b32 p, %38, 0;\n"
      "mov.b64 db, {%36, %37};\n"
      "wgmma.mma_async.sync.aligned.m64n64k16.f32.bf16.bf16 {"
      "%0, %1, %2, %3, %4, %5, %6, %7, %8, %9, %10, %11, %12, %13, %14, %15, "
      "%16, %17, %18, %19, %20, %21, %22, %23, %24, %25, %26, %27, %28, %29, %30, %31"
      "}, {%32, %33, %34, %35}, db, p, 1, 1, 1;\n}\n"
      : "=f"(d[0]), "=f"(d[1]), "=f"(d[2]), "=f"(d[3]), "=f"(d[4]), "=f"(d[5]), "=f"(d[6]), "=f"(d[7]),
        "=f"(d[8]), "=f"(d[9]), "=f"(d[10]), "=f"(d[11]), "=f"(d[12]), "=f"(d[13]), "=f"(d[14]), "=f"(d[15]),
        "=f"(d[16]), "=f"(d[17]), "=f"(d[18]), "=f"(d[19]), "=f"(d[20]), "=f"(d[21]), "=f"(d[22]), "=f"(d[23]),
        "=f"(d[24]), "=f"(d[25]), "=f"(d[26]), "=f"(d[27]), "=f"(d[28]), "=f"(d[29]), "=f"(d[30]), "=f"(d[31])
      : "r"(a[0]), "r"(a[1]), "r"(a[2]), "r"(a[3]), "r"(db), "n"(HB), "n"(0));
  }
};
template <> struct WgSST<48> {
  template <uint32_t HA, uint32_t HB>
  static __device__ __forceinline__ void mma(float* d, uint32_t da, uint32_t db, int sc) {
    asm volatile("{\n.reg .pred p;\n.reg .b64 da, db;\nsetp.ne.b32 p, %28, 0;\n"
      "mov.b64 da, {%24, %25};\nmov.b64 db, {%26, %27};\n"
      "wgmma.mma_async.sync.aligned.m64n48k16.f32.bf16.bf16 {"
      "%0, %1, %2, %3, %4, %5, %6, %7, %8, %9, %10, %11, %12, %13, %14, %15, "
      "%16, %17, %18, %19, %20, %21, %22, %23"
      "}, da, db, p, 1, 1, 0, 1;\n}\n"
      : "+f"(d[0]), "+f"(d[1]), "+f"(d[2]), "+f"(d[3]), "+f"(d[4]), "+f"(d[5]), "+f"(d[6]), "+f"(d[7]),
        "+f"(d[8]), "+f"(d[9]), "+f"(d[10]), "+f"(d[11]), "+f"(d[12]), "+f"(d[13]), "+f"(d[14]), "+f"(d[15]),
        "+f"(d[16]), "+f"(d[17]), "+f"(d[18]), "+f"(d[19]), "+f"(d[20]), "+f"(d[21]), "+f"(d[22]), "+f"(d[23])
      : "r"(da), "n"(HA), "r"(db), "n"(HB), "r"(sc));
  }
};
template <> struct WgSST<80> {
  template <uint32_t HA, uint32_t HB>
  static __device__ __forceinline__ void mma(float* d, uint32_t da, uint32_t db, int sc) {
    asm volatile("{\n.reg .pred p;\n.reg .b64 da, db;\nsetp.ne.b32 p, %44, 0;\n"
      "mov.b64 da, {%40, %41};\nmov.b64 db, {%42, %43};\n"
      "wgmma.mma_async.sync.aligned.m64n80k16.f32.bf16.bf16 {"
      "%0, %1, %2, %3, %4, %5, %6, %7, %8, %9, %10, %11, %12, %13, %14, %15, "
      "%16, %17, %18, %19, %20, %21, %22, %23, %24, %25, %26, %27, %28, %29, %30, %31, "
      "%32, %33, %34, %35, %36, %37, %38, %39"
      "}, da, db, p, 1, 1, 0, 1;\n}\n"
      : "+f"(d[0]), "+f"(d[1]), "+f"(d[2]), "+f"(d[3]), "+f"(d[4]), "+f"(d[5]), "+f"(d[6]), "+f"(d[7]),
        "+f"(d[8]), "+f"(d[9]), "+f"(d[10]), "+f"(d[11]), "+f"(d[12]), "+f"(d[13]), "+f"(d[14]), "+f"(d[15]),
        "+f"(d[16]), "+f"(d[17]), "+f"(d[18]), "+f"(d[19]), "+f"(d[20]), "+f"(d[21]), "+f"(d[22]), "+f"(d[23]),
        "+f"(d[24]), "+f"(d[25]), "+f"(d[26]), "+f"(d[27]), "+f"(d[28]), "+f"(d[29]), "+f"(d[30]), "+f"(d[31]),
        "+f"(d[32]), "+f"(d[33]), "+f"(d[34]), "+f"(d[35]), "+f"(d[36]), "+f"(d[37]), "+f"(d[38]), "+f"(d[39])
      : "r"(da), "n"(HA), "r"(db), "n"(HB), "r"(sc));
  }
};
template <> struct WgSST<192> {
  template <uint32_t HA, uint32_t HB>
  static __device__ __forceinline__ void mma(float* d, uint32_t da, uint32_t db, int sc) {
    asm volatile("{\n.reg .pred p;\n.reg .b64 da, db;\nsetp.ne.b32 p, %100, 0;\n"
      "mov.b64 da, {%96, %97};\nmov.b64 db, {%98, %99};\n"
      "wgmma.mma_async.sync.aligned.m64n192k16.f32.bf16.bf16 {"
      "%0, %1, %2, %3, %4, %5, %6, %7, %8, %9, %10, %11, %12, %13, %14, %15, "
      "%16, %17, %18, %19, %20, %21, %22, %23, %24, %25, %26, %27, %28, %29, %30, %31, "
      "%32, %33, %34, %35, %36, %37, %38, %39, %40, %41, %42, %43, %44, %45, %46, %47, "
      "%48, %49, %50, %51, %52, %53, %54, %55, %56, %57, %58, %59, %60, %61, %62, %63, "
      "%64, %65, %66, %67, %68, %69, %70, %71, %72, %73, %74, %75, %76, %77, %78, %79, "
      "%80, %81, %82, %83, %84, %85, %86, %87, %88, %89, %90, %91, %92, %93, %94, %95"
      "}, da, db, p, 1, 1, 0, 1;\n}\n"
      : "+f"(d[0]), "+f"(d[1]), "+f"(d[2]), "+f"(d[3]), "+f"(d[4]), "+f"(d[5]), "+f"(d[6]), "+f"(d[7]),
        "+f"(d[8]), "+f"(d[9]), "+f"(d[10]), "+f"(d[11]), "+f"(d[12]), "+f"(d[13]), "+f"(d[14]), "+f"(d[15]),
        "+f"(d[16]), "+f"(d[17]), "+f"(d[18]), "+f"(d[19]), "+f"(d[20]), "+f"(d[21]), "+f"(d[22]), "+f"(d[23]),
        "+f"(d[24]), "+f"(d[25]), "+f"(d[26]), "+f"(d[27]), "+f"(d[28]), "+f"(d[29]), "+f"(d[30]), "+f"(d[31]),
        "+f"(d[32]), "+f"(d[33]), "+f"(d[34]), "+f"(d[35]), "+f"(d[36]), "+f"(d[37]), "+f"(d[38]), "+f"(d[39]),
        "+f"(d[40]), "+f"(d[41]), "+f"(d[42]), "+f"(d[43]), "+f"(d[44]), "+f"(d[45]), "+f"(d[46]), "+f"(d[47]),
        "+f"(d[48]), "+f"(d[49]), "+f"(d[50]), "+f"(d[51]), "+f"(d[52]), "+f"(d[53]), "+f"(d[54]), "+f"(d[55]),
        "+f"(d[56]), "+f"(d[57]), "+f"(d[58]), "+f"(d[59]), "+f"(d[60]), "+f"(d[61]), "+f"(d[62]), "+f"(d[63]),
        "+f"(d[64]), "+f"(d[65]), "+f"(d[66]), "+f"(d[67]), "+f"(d[68]), "+f"(d[69]), "+f"(d[70]), "+f"(d[71]),
        "+f"(d[72]), "+f"(d[73]), "+f"(d[74]), "+f"(d[75]), "+f"(d[76]), "+f"(d[77]), "+f"(d[78]), "+f"(d[79]),
        "+f"(d[80]), "+f"(d[81]), "+f"(d[82]), "+f"(d[83]), "+f"(d[84]), "+f"(d[85]), "+f"(d[86]), "+f"(d[87]),
        "+f"(d[88]), "+f"(d[89]), "+f"(d[90]), "+f"(d[91]), "+f"(d[92]), "+f"(d[93]), "+f"(d[94]), "+f"(d[95])
      : "r"(da), "n"(HA), "r"(db), "n"(HB), "r"(sc));
  }
};

struct FftConst {
  uint32_t f[2][4], fi[4][4];
  uint32_t ta[2][2], tb[2][2];
};
__device__ __forceinline__ void cis(int m, float scale, float& c, float& s) {
  const float a = (float)m * (-6.283185307179586f * scale);
  c = __cosf(a);
  s = __sinf(a);
}
__device__ __forceinline__ void fft_tables(uint32_t (&v)[12], int tw) {
  const int row = tw >> 2, ch = tw & 3;
#pragma unroll
  for (int i = 0; i < 4; i++) {
    float c[2], s[2], x[2];
#pragma unroll
    for (int e = 0; e < 2; e++) {
      cis((((32 * (8 * ch + 2 * i + e) + 15) * (4 * row - 63) + 2048) & 4095) - 2048, 1.f / 4096, c[e], s[e]);
      float gc, gs;
      cis((((row & 15) * (8 * (ch & 1) + 2 * i + e) + 8) & 15) - 8, 1.f / 16, gc, gs);
      x[e] = (row >> 4) == (ch >> 1) ? gc : (ch >> 1) ? gs : -gs;
    }
    v[i] = pack2(c[0] * 0.125f, c[1] * 0.125f);
    v[4 + i] = pack2(s[0] * 0.125f, s[1] * 0.125f);
    v[8 + i] = pack2(x[0], x[1]);
  }
#pragma unroll
  for (int i = 0; i < 12; i++) asm volatile("" : "+r"(v[i]));
}
__device__ __forceinline__ void fft_tables_store(const uint32_t (&v)[12], uint32_t sb, int tw) {
  const int row = tw >> 2;
  const uint32_t x = ((tw ^ (row >> 1)) & 3) << 4, a = sb + OFF_FT + (16 * (row >> 3) + (row & 7)) * 64 + x;
  sts128(a, v[0], v[1], v[2], v[3]);
  sts128(a + 512, v[4], v[5], v[6], v[7]);
  sts128(sb + OFF_GT + row * 64 + x, v[8], v[9], v[10], v[11]);
}
__device__ __forceinline__ void fft_twiddles(uint32_t (&v)[2], int tw) {
  float a[2], s[2];
#pragma unroll
  for (int i = 0; i < 2; i++) {
    float c;
    cis((2 * (2 * (tw & 3) + i) - 15) * (4 * (tw >> 2) - 63), 1.f / 4096, c, s[i]);
    a[i] = __fdividef(-s[i], 1.f + c);
  }
  v[0] = pack2(a[0], a[1]);
  v[1] = pack2(s[0], s[1]);
  asm volatile("" : "+r"(v[0]), "+r"(v[1]));
}
__device__ __forceinline__ void fft_matrices(FftConst& k, uint32_t sb, int w, int lane) {
  const uint32_t x = (lane >> 1) & 3;
  const uint2 t0 = lds64(sb + OFF_TT + 256 * w + 8 * lane), t1 = lds64(sb + OFF_TT + 256 * w + 8 * (lane ^ 3));
  k.ta[0][0] = t0.x;
  k.tb[0][0] = t0.y;
  k.ta[1][1] = __byte_perm(t1.x, 0, 0x1032);
  k.tb[1][1] = __byte_perm(t1.y, 0, 0x1032);
#pragma unroll
  for (int j = 0; j < 2; j++) {
    k.ta[1 - j][j] = k.ta[j][j] ^ 0x80008000u;
    k.tb[1 - j][j] = k.tb[j][j] ^ 0x80008000u;
    asm volatile("" : "+r"(k.ta[0][j]), "+r"(k.tb[0][j]), "+r"(k.ta[1][j]), "+r"(k.tb[1][j]));
  }
#pragma unroll
  for (int i = 0; i < 2; i++) {
    ldsm4(k.f[i], sb + OFF_FT + (16 * w + (lane & 15)) * 64 + (((2 * i + (lane >> 4)) ^ x) << 4));
    ldsm4t(k.fi[i], sb + OFF_FT + (32 * i + lane) * 64 + ((w ^ x) << 4));
#pragma unroll
    for (int j = 0; j < 4; j++) {
      k.fi[2 + i][j] = (j & 1) ? k.fi[i][j - 1] ^ 0x80008000u : k.fi[i][j + 1];
      asm volatile("" : "+r"(k.fi[2 + i][j]));
    }
  }
}
__device__ __forceinline__ void rot(uint32_t& x, uint32_t& y, uint32_t a, uint32_t b) {
  x = bfma(a, y, x);
  y = bfma(b, x, y);
  x = bfma(a, y, x);
}
__device__ __forceinline__ void twiddle_fwd(uint32_t (&a)[4][4], float* d, const FftConst& k) {
#pragma unroll
  for (int q = 0; q < 4; q++)
#pragma unroll
    for (int j = 0; j < 2; j++) {
      const float* x = d + 8 * q + 4 * j;
      uint32_t re = pack2(x[0], x[1]), im = pack2(x[2], x[3]);
      rot(re, im, k.ta[0][j], k.tb[0][j]);
      a[q & 2][2 * j + (q & 1)] = re;
      a[(q & 2) + 1][2 * j + (q & 1)] = im;
    }
}
__device__ __forceinline__ void g_step(float* d, const uint32_t (&a)[4][4], uint32_t dre, uint32_t dim) {
  WgRS<32>::set<HI_SW64>(d, a[0], dre);
  WgRS<32>::set<HI_SW64>(d + 16, a[2], dre);
  WgRS<32>::mma<HI_SW64>(d, a[1], dim);
  WgRS<32>::mma<HI_SW64>(d + 16, a[3], dim);
  wg_commit();
}

__device__ __forceinline__ void products(uint32_t (&a)[4][4], const float* H, const float* U, int p) {
#pragma unroll
  for (int j = 0; j < 2; j++)
#pragma unroll
    for (int m = 2 * p; m < 2 * p + 2; m++) {
      float pr[2], pi[2];
#pragma unroll
      for (int x = 0; x < 2; x++)
#pragma unroll
        for (int q = 0; q <= m; q++) {
          const int ih = 16 * (q >> 1) + 2 * (q & 1) + 4 * j + x, iu = 16 * ((m - q) >> 1) + 2 * ((m - q) & 1) + 4 * j + x;
          pr[x] = q ? fmaf(H[ih], U[iu], pr[x]) : H[ih] * U[iu];
          pi[x] = q ? fmaf(H[ih], U[iu + 8], pi[x]) : H[ih] * U[iu + 8];
          pr[x] = fmaf(-H[ih + 8], U[iu + 8], pr[x]);
          pi[x] = fmaf(H[ih + 8], U[iu], pi[x]);
        }
      a[m & 2][2 * j + (m & 1)] = pack2(pr[0], pr[1]);
      a[(m & 2) + 1][2 * j + (m & 1)] = pack2(pi[0], pi[1]);
    }
}

__device__ __forceinline__ void conv_channel(const FftConst& k, uint32_t sb, int c, int wg, int w, int lane) {
  const uint32_t cb = sb + off_ch(c), bars = sb + OFF_BAR;
  const uint32_t du = desc_lo(cb, 1024), dg = desc_lo(sb + OFF_GT, 16), dz = desc_lo(cb + U_BYTES, 16);
  float U[32], H[32];
  uint32_t a[4][4], e[4][4];
  const float dv = __uint_as_float(lds32(sb + OFF_D + 4 * c));
  wg_fence();
  WgRS<64>::set<HI_SW32>(H, k.f[0], du + 256);
  WgRS<64>::mma<HI_SW32>(H, k.f[1], du + 256 + 32);
  wg_commit();
  wg_wait<0>();
  pin<32>(H);
  twiddle_fwd(a, H, k);
  mbar_wait(bars + 8 * (B_U + (c < 3 ? c : 3)), 0);
  TSM(w == 0 && c < 3, 7 + wg);
  wg_fence();
  WgRS<64>::set<HI_SW32>(U, k.f[0], du);
  WgRS<64>::mma<HI_SW32>(U, k.f[1], du + 32);
  wg_commit();
  g_step(H, a, dg, dg + 64);
  wg_wait<1>();
  pin<32>(U);
  twiddle_fwd(e, U, k);
  wg_fence();
  g_step(U, e, dg, dg + 64);
  wg_wait<0>();
  pin<32>(U);
  pin<32>(H);
#pragma unroll
  for (int j = 0; j < 4; j++) H[4 * (j >> 1) + (j & 1)] += dv;
  float V[32];
#pragma unroll
  for (int p = 0; p < 2; p++) {
    products(a, H, U, p);
    wg_fence();
    WgRS<32>::set<HI_SW64>(V + 16 * p, a[2 * p], dg + 64);
    WgRS<32>::mma<HI_SW64>(V + 16 * p, a[2 * p + 1], dg);
    wg_commit();
  }
  const uint32_t za = cb + U_BYTES + (8 * w + (lane & 7)) * 128 + (((lane >> 3) ^ (lane & 7)) << 4);
  const uint32_t ya = cb + (lane >> 4) * 1024 + (8 * w + (lane & 7)) * 32 + ((((lane >> 3) ^ (lane >> 2)) & 1) << 4);
  wg_sync(1 + wg);
#pragma unroll
  for (int p = 0; p < 2; p++) {
    if (p == 0) wg_wait<1>();
    else wg_wait<0>();
    pin<16>(V + 16 * p);
#pragma unroll
    for (int i = 0; i < 4; i++) {
      const int j = i & 1;
      const float* x = V + 16 * p + 4 * j + (i & 2);
      e[p][i] = pack2(x[8], x[9]);
      e[2 + p][i] = pack2(x[0], x[1]);
      rot(e[p][i], e[2 + p][i], k.ta[1][j], k.tb[1][j]);
    }
    stsm4(za ^ (64 * p), e[p]);
    stsm4((za ^ (64 * p)) + 4096, e[2 + p]);
  }
  fence_async_smem();
  wg_sync(1 + wg);
  wg_fence();
  WgRS<64>::set<HI_SW128>(H, k.fi[0], dz);
#pragma unroll
  for (int ks = 1; ks < 4; ks++) WgRS<64>::mma<HI_SW128>(H, k.fi[ks], dz + 128 * ks);
  wg_commit();
  wg_wait<0>();
  pin<32>(H);
  if (lane == 0) mbar_arrive(bars + 8 * B_CVD);
  TSIF(w == 0, 88 + c);
#pragma unroll
  for (int j = 0; j < 8; j++)
    a[j >> 2][j & 3] = j < 2 ? pack2(H[4 * j], H[4 * j + 1]) : pack2(H[4 * j] + H[4 * j - 6], H[4 * j + 1] + H[4 * j - 5]);
  stsm4(ya, a[0]);
  stsm4(ya + 2048, a[1]);
  fence_async_smem();
  __syncwarp();
}

__device__ __forceinline__ void prep_slab(uint4* res, const uint2* sw, uint32_t sb, int slab, int w, int lane) {
  const int t = lane & 3, tp = (lane & 7) >> 1, pos = 8 * tp + 2 * (((lane >> 3) + tp) & 3) + (lane & 1);
  const uint32_t base = sb + OFF_KVS + slab * KVS_BYTES + pos * 128;
  uint32_t kk[2][4][4], vv[2][4];
  mbar_wait(sb + OFF_BAR + 8 * (B_KV + slab), 0);
#pragma unroll
  for (int h = 0; h < 2; h++) {
#pragma unroll
    for (int j = 0; j < 4; j++) {
      const uint32_t a = base + 128 * j;
      ldsm4t(kk[h][j], a + (((w + 4 * h) ^ ((a >> 7) & 7)) << 4));
    }
    const uint32_t a = base + KVS_V;
    ldsm4t(vv[h], a + (((w + 4 * h) ^ ((a >> 7) & 7)) << 4));
  }
#pragma unroll
  for (int h = 0; h < 2; h++) {
    uint32_t (&k)[4][4] = kk[h];
    uint32_t (&v)[4] = vv[h];
    const uint32_t w0 = __byte_perm(sw[h].x, 0, 0x1010), w1 = __byte_perm(sw[h].x, 0, 0x3232);
    const uint32_t w2 = __byte_perm(sw[h].y, 0, 0x1010), w3 = __byte_perm(sw[h].y, 0, 0x3232);
#pragma unroll
    for (int m = 0; m < 4; m++)
      v[m] = bmul(badd(badd(badd(bmul(k[0][m], w3), bmul(k[1][m], w2)), bmul(k[2][m], w1)), bmul(k[3][m], w0)), v[m]);
    uint32_t a[4];
#pragma unroll
    for (int m = 0; m < 4; m++) a[m] = (t & 1) ? v[(m + 3) & 3] : v[m];
    res[h] = (t & 2) ? make_uint4(a[2], a[3], a[0], a[1]) : make_uint4(a[0], a[1], a[2], a[3]);
  }
}

__device__ __forceinline__ void prep_gate(const Params& p, uint32_t sb, int b, int w, int lane) {
  uint2 gw[5], x[4][5];
#pragma unroll
  for (int j = 0; j < 5; j++) gw[j] = ldg64(reinterpret_cast<const uint2*>(p.gate_w) + lane + 32 * j);
#pragma unroll
  for (int i = 0; i < 4; i++)
#pragma unroll
    for (int j = 0; j < 5; j++)
      x[i][j] = ldg64(reinterpret_cast<const uint2*>(p.q) + (16 * b + 4 * w + i) * (DIM / 4) + lane + 32 * j);
  float s[4];
#pragma unroll
  for (int i = 0; i < 4; i++) {
    s[i] = 0.f;
#pragma unroll
    for (int j = 0; j < 5; j++) {
      const uint32_t m0 = bmul(x[i][j].x, gw[j].x), m1 = bmul(x[i][j].y, gw[j].y);
      s[i] += (bf_lo(m0) + bf_hi(m0)) + (bf_lo(m1) + bf_hi(m1));
    }
  }
  const bool h = lane & 16, q = lane & 8;
  const float a = (h ? s[2] : s[0]) + __shfl_xor_sync(0xffffffffu, h ? s[0] : s[2], 16);
  const float c = (h ? s[3] : s[1]) + __shfl_xor_sync(0xffffffffu, h ? s[1] : s[3], 16);
  float z = (q ? c : a) + __shfl_xor_sync(0xffffffffu, q ? a : c, 8);
#pragma unroll
  for (int o = 4; o > 0; o >>= 1) z += __shfl_xor_sync(0xffffffffu, z, o);
  z = bf_lo(pack2(z, 0.f));
  z = bf_lo(pack2(__fdividef(1.f, 1.f + __expf(-z)), 0.f));
  mbar_wait(sb + OFF_BAR + 8 * B_S3, 0);
  if ((lane & 7) == 0) asm volatile("st.shared.f32 [%0], %1;" ::"r"(sb + OFF_GATE + 64 * (b & 7) + 16 * w + (lane >> 1)), "f"(z) : "memory");
  fence_async_smem();
}

__device__ __forceinline__ uint32_t bmax(uint32_t a, uint32_t b) {
  uint32_t d;
  asm("max.bf16x2 %0, %1, %2;" : "=r"(d) : "r"(a), "r"(b));
  return d;
}
__device__ __forceinline__ void softmax_two(const float (&l)[2][2], uint32_t& p0, uint32_t& p1) {
  constexpr float kScale = 0.22360679774997896f, kLog2e = 1.4426950408889634f;
  const uint32_t r0 = pack2(l[0][0], l[1][0]), r1 = pack2(l[0][1], l[1][1]);
  const uint32_t x0 = pack2(bf_lo(r0) * kScale, bf_hi(r0) * kScale), x1 = pack2(bf_lo(r1) * kScale, bf_hi(r1) * kScale);
  uint32_t m = bmax(x0, x1);
  m = bmax(m, __shfl_xor_sync(0xffffffffu, m, 1));
  m = bmax(m, __shfl_xor_sync(0xffffffffu, m, 2));
  const float m0 = bf_lo(m) * kLog2e, m1 = bf_hi(m) * kLog2e;
  p0 = pack2(ex2(bf_lo(x0) * kLog2e - m0), ex2(bf_lo(x1) * kLog2e - m0));
  p1 = pack2(ex2(bf_hi(x0) * kLog2e - m1), ex2(bf_hi(x1) * kLog2e - m1));
}

__device__ __forceinline__ void halo_read(uint32_t (&kpv)[10], uint32_t (&vpv)[10], uint32_t (&tg)[7], const uint4* hp) {
#pragma unroll
  for (int j = 0; j < 7; j++) {
    uint32_t x0, x1, x2;
    asm volatile("ld.relaxed.gpu.global.v4.u32 {%0, %1, %2, %3}, [%4];"
                 : "=r"(x0), "=r"(x1), "=r"(x2), "=r"(tg[j]) : "l"(hp + 32 * j) : "memory");
    if (j < 4) kpv[3 * j] = x0; else vpv[3 * j - 10] = x0;
    if (j < 3) kpv[3 * j + 1] = x1; else vpv[3 * j - 9] = x1;
    if (j < 3) kpv[3 * j + 2] = x2; else if (j < 6) vpv[3 * j - 8] = x2;
  }
}

template <int ROT>
__device__ __forceinline__ void pack_qkv(const float* acc, uint32_t (&qlo)[10], uint32_t (&qhi)[10], uint32_t (&klo)[10],
                                         uint32_t (&khi)[10], uint32_t (&vlo)[10], uint32_t (&vhi)[10]) {
#pragma unroll
  for (int j = 0; j < 10; j++) {
    const int x = (j + ROT) % 10, tq = x < 8 ? x : 16 + x, tk = x < 8 ? 8 + x : 18 + x, tv = x < 8 ? 16 + x : 20 + x;
    khi[j] = pack2(acc[4 * tk + 2], acc[4 * tk + 3]);
    vhi[j] = movm(pack2(acc[4 * tv + 2], acc[4 * tv + 3]));
    qlo[j] = pack2(acc[4 * tq], acc[4 * tq + 1]);
    qhi[j] = pack2(acc[4 * tq + 2], acc[4 * tq + 3]);
    klo[j] = pack2(acc[4 * tk], acc[4 * tk + 1]);
    vlo[j] = pack2(acc[4 * tv], acc[4 * tv + 1]);
    asm volatile("" : "+r"(khi[j]), "+r"(qlo[j]), "+r"(qhi[j]), "+r"(klo[j]), "+r"(vlo[j]));
  }
}

template <int ROT> __device__ __forceinline__ void halo_send(const float* acc, uint4* ho, uint32_t tag) {
#pragma unroll
  for (int j = 0; j < 7; j++) {
    uint32_t x[3];
#pragma unroll
    for (int e = 0; e < 3; e++) {
      const int i = 3 * j + e, y = (i % 10 + ROT) % 10, tk = y < 8 ? 8 + y : 18 + y, tv = y < 8 ? 16 + y : 20 + y;
      x[e] = i < 10 ? pack2(acc[4 * tk + 2], acc[4 * tk + 3]) : i < 20 ? movm(pack2(acc[4 * tv + 2], acc[4 * tv + 3])) : 0u;
    }
    asm volatile("st.relaxed.gpu.global.v4.u32 [%0], {%1, %2, %3, %4};" ::"l"(ho + 32 * j), "r"(x[0]), "r"(x[1]), "r"(x[2]), "r"(tag) : "memory");
  }
}

__device__ __forceinline__ void attention(float* acc, uint32_t sb, int b, int par, int w, int lane, uint32_t tag) {
  const int g = lane >> 2, t = lane & 3;
  uint32_t klo[10], khi[10], vlo[10], vhi[10], qlo[10], qhi[10], kpv[10], vpv[10];
  if (w == 3 && b < NCTA - 8) {
    uint4* ho = g_halo + (b * 2 + par) * 224 + lane;
    if (tail_first(b & 7)) halo_send<8>(acc, ho, tag);
    else halo_send<0>(acc, ho, tag);
    TSIF(par == 0, 76);
    pin<120>(acc);
  }
  if (tail_first(b & 7)) pack_qkv<8>(acc, qlo, qhi, klo, khi, vlo, vhi);
  else pack_qkv<0>(acc, qlo, qhi, klo, khi, vlo, vhi);
  const uint32_t xa = sb + OFF_KVX + (par * 3) * 2560 + lane * 16;
  if (w < 3) {
    sts128(xa + w * 2560, khi[0], khi[1], khi[2], khi[3]);
    sts128(xa + w * 2560 + 512, khi[4], khi[5], khi[6], khi[7]);
    sts128(xa + w * 2560 + 1024, khi[8], khi[9], vhi[0], vhi[1]);
    sts128(xa + w * 2560 + 1536, vhi[2], vhi[3], vhi[4], vhi[5]);
    sts128(xa + w * 2560 + 2048, vhi[6], vhi[7], vhi[8], vhi[9]);
  }
  TSIF(par == 0 && w == 1, 64);
#pragma unroll
  for (int j = 0; j < 10; j++) vlo[j] = movm(vlo[j]);
  const bool far0 = 2 * t > g, far1 = 2 * t + 1 > g;
  const uint32_t mfar = (far0 ? 0x0000FFFFu : 0u) | (far1 ? 0xFFFF0000u : 0u);
  float slo[4][2], lg[2][2];
  uint32_t phi[4], plo[4], qml[4], qmh[4];
  const bool nohist = (w == 0) && (b < 8);
  const uint4* hp = g_halo + ((b - 8) * 2 + par) * 224 + lane;
  uint32_t tg[7];
#pragma unroll
  for (int h = 0; h < 4; h++) {
    if (h == HR_AT && w == 0 && !nohist) halo_read(kpv, vpv, tg, hp);
    const int f = h == 0 ? 0 : h == 1 ? 3 : h == 2 ? 5 : 8, hf = h < 2 ? 2 : 7;
    const bool mine = (h & 1) ? t >= 2 : t < 2;
    qml[h] = mine ? qlo[hf] : 0u;
    qmh[h] = mine ? qhi[hf] : 0u;
    float a[4] = {0.f, 0.f, 0.f, 0.f}, c[4] = {0.f, 0.f, 0.f, 0.f};
    mma16816(a, qlo[f], qhi[f], qlo[f + 1], qhi[f + 1], klo[f], klo[f + 1]);
    mma16816(c, qlo[f], qhi[f], qlo[f + 1], qhi[f + 1], khi[f], khi[f + 1]);
    mma1688(a, qml[h], qmh[h], klo[hf]);
    mma1688(c, qml[h], qmh[h], khi[hf]);
    slo[h][0] = a[0];
    slo[h][1] = a[1];
    lg[h & 1][0] = far0 ? a[2] : c[2];
    lg[h & 1][1] = far1 ? a[3] : c[3];
    if (h & 1) softmax_two(lg, phi[h - 1], phi[h]);
  }
  if (HR_AT == 4 && w == 0 && !nohist) halo_read(kpv, vpv, tg, hp);
  TSIF(par == 0 && w == 1, 65);
  wg_sync(1 + par);
  TSIF(par == 0 && w == 1, 66);
  if (w > 0) {
    const uint4 v0 = lds128(xa + (w - 1) * 2560), v1 = lds128(xa + (w - 1) * 2560 + 512), v2 = lds128(xa + (w - 1) * 2560 + 1024);
    const uint4 v3 = lds128(xa + (w - 1) * 2560 + 1536), v4 = lds128(xa + (w - 1) * 2560 + 2048);
    kpv[0] = v0.x; kpv[1] = v0.y; kpv[2] = v0.z; kpv[3] = v0.w; kpv[4] = v1.x; kpv[5] = v1.y; kpv[6] = v1.z; kpv[7] = v1.w;
    kpv[8] = v2.x; kpv[9] = v2.y; vpv[0] = v2.z; vpv[1] = v2.w; vpv[2] = v3.x; vpv[3] = v3.y; vpv[4] = v3.z; vpv[5] = v3.w;
    vpv[6] = v4.x; vpv[7] = v4.y; vpv[8] = v4.z; vpv[9] = v4.w;
  } else if (nohist) {
#pragma unroll
    for (int j = 0; j < 10; j++) kpv[j] = vpv[j] = 0u;
  } else if (HR_AT == 5) {
    TSIF(par == 0, 77);
    halo_read(kpv, vpv, tg, hp);
  }
  if (w == 0 && !nohist) {
    int spins = 0;
    while (true) {
      bool ok = true;
#pragma unroll
      for (int j = 0; j < 7; j++) ok = ok && tg[j] == tag;
      if (__all_sync(0xffffffffu, ok) || ++spins > SPIN_LIMIT) break;
      halo_read(kpv, vpv, tg, hp);
    }
    TSIF(par == 0, 79);
  }
#pragma unroll
  for (int h = 0; h < 4; h++) {
    const int f = h == 0 ? 0 : h == 1 ? 3 : h == 2 ? 5 : 8, hf = h < 2 ? 2 : 7;
    float a[4] = {0.f, 0.f, 0.f, 0.f};
    mma16816(a, qlo[f], qhi[f], qlo[f + 1], qhi[f + 1], kpv[f], kpv[f + 1]);
    mma1688(a, qml[h], qmh[h], kpv[hf]);
    const float ninf = __int_as_float(0xff800000);
    lg[h & 1][0] = far0 ? (nohist ? ninf : a[0]) : slo[h][0];
    lg[h & 1][1] = far1 ? (nohist ? ninf : a[1]) : slo[h][1];
    if (h & 1) softmax_two(lg, plo[h - 1], plo[h]);
  }
  TSIF(par == 0 && w <= 1, 67 + w);
  uint32_t ov[20];
#pragma unroll
  for (int hp = 0; hp < 2; hp++) {
    const int hf = hp ? 7 : 2;
    float sh[4] = {0.f, 0.f, 0.f, 0.f}, i0 = 0.f, i1 = 0.f;
#pragma unroll
    for (int e = 0; e < 2; e++) {
      const int h = 2 * hp + e, f = h == 0 ? 0 : h == 1 ? 3 : h == 2 ? 5 : 8;
      const uint32_t a0 = plo[h] & mfar, a2 = plo[h] & ~mfar, a3 = phi[h] & mfar, c1 = phi[h] & ~mfar;
      float sum[4] = {0.f, 0.f, 0.f, 0.f};
      mma1688(sum, plo[h], phi[h], 0x3F803F80u);
      const float r0 = rcp(sum[0]), r1 = rcp(sum[2]);
#pragma unroll
      for (int j = f; j < f + 2; j++) {
        float o[4] = {0.f, 0.f, 0.f, 0.f};
        mma16816(o, a0, 0u, a2, a3, vpv[j], vlo[j]);
        mma1688(o, 0u, c1, vhi[j]);
        ov[2 * j] = pack2(o[0] * r0, o[1] * r0);
        ov[2 * j + 1] = pack2(o[2] * r1, o[3] * r1);
      }
      const bool mine = e ? g >= 4 : g < 4;
      mma16816(sh, a0, 0u, a2, a3, mine ? vpv[hf] : 0u, mine ? vlo[hf] : 0u);
      mma1688(sh, 0u, c1, mine ? vhi[hf] : 0u);
      if (e == 0 || t >= 2) {
        i0 = r0;
        i1 = r1;
      }
    }
    ov[2 * hf] = pack2(sh[0] * i0, sh[1] * i0);
    ov[2 * hf + 1] = pack2(sh[2] * i1, sh[3] * i1);
  }
  TS(32 + 4 * par + w);
  mbar_wait(sb + OFF_BAR + 8 * B_P1, 0);
  const uint32_t oa = sb + OFF_OA + (lane >> 4) * 2048 + (32 * w + 2 * (lane & 15) + par) * 16;
#pragma unroll
  for (int j = 0; j < 5; j++) stsm4(oa + 4096 * j, ov + 4 * j);
  TSIF(par == 0 && w == 0, 120);
  fence_async_smem();
  TSIF(par == 0 && w == 0, 121);
  __syncwarp();
  if (lane == 0) mbar_arrive(sb + OFF_BAR + 8 * B_ATTN);
  TSM(w == 0 || w == 2, 122 + par + (w == 2 ? 3 : 0));
}

struct Maps {
  CUtensorMap x, wm, wt, k, v, y, wo, qm, qt, om, ot, yl, ol;
};

__device__ __forceinline__ void load_stage(uint32_t sb, int kb, int b, const Maps& m) {
  const uint32_t st = sb + (kb & 3) * STAGE_BYTES, bar = sb + OFF_BAR + 8 * (B_FULL1 + (kb & 3));
  const int r = b >> 3, hg = b & 7, slab = kb - KV_KB;
  const bool kv = slab >= 0 && slab < 5;
  const uint32_t kbar = sb + OFF_BAR + 8 * (B_KV + slab), dst = sb + OFF_KVS + slab * KVS_BYTES;
  mbar_expect_tx(bar, STAGE_BYTES);
  if (kv) mbar_expect_tx(kbar, KVS_BYTES);
  tma_3d(st, &m.x, 64 * kb, 64 * r, 0, bar);
  tma_3d(st + ST_W, &m.wm, 80 * hg + (tail_first(hg) ? 16 : 0), 64 * kb, 0, bar);
  tma_3d(st + ST_WT, &m.wt, 80 * hg + (tail_first(hg) ? 0 : 64), 64 * kb, 0, bar);
  if (kv) tma_3d(dst, &m.k, 0, 32 * (b >> 1) - 3, 2 * slab + (b & 1), kbar);
  if (kv) tma_3d(dst + KVS_V, &m.v, 0, 32 * (b >> 1), 2 * slab + (b & 1), kbar);
}

__global__ void __launch_bounds__(NTHR, 1) fused_kernel(const __grid_constant__ Maps m, const Params p) {
  extern __shared__ __align__(1024) uint8_t smem[];
  const uint32_t sb = (uint32_t)__cvta_generic_to_shared(smem);
  const uint32_t bars = sb + OFF_BAR;
  const int tid = threadIdx.x, lane = tid & 31;
  int b = blockIdx.x;
  b = (((b & 63) >> 3) * 2 + (b & 1)) * 8 + (((b < 64 ? 0x6521 : 0x7430) >> (4 * ((b >> 1) & 3))) & 7);
  const int r = b >> 3, hg = b & 7;

  if (tid == T_ISSUE) {
    TSM(true, 0);
    mbar_init(bars + 8 * B_F0, 1);
    fence_async_smem();
    mbar_expect_tx(bars + 8 * B_F0, ST_WT);
    tma_3d(sb, &m.x, 0, 64 * r, 0, bars + 8 * B_F0);
    tma_3d(sb + ST_W, &m.wm, 80 * hg + (tail_first(hg) ? 16 : 0), 0, 0, bars + 8 * B_F0);
#pragma unroll
    for (int i = 0; i < 4; i++) mbar_init(bars + 8 * (B_FULL1 + i), 1);
    fence_async_smem();
    mbar_expect_tx(bars + 8 * B_FULL1, STAGE_BYTES - ST_WT);
    tma_3d(sb + ST_WT, &m.wt, 80 * hg + (tail_first(hg) ? 0 : 64), 0, 0, bars + 8 * B_FULL1);
    load_stage(sb, 1, b, m);
  } else if (tid == T_INIT) {
#pragma unroll
    for (int i = 0; i < B_F0; i++) mbar_init(bars + 8 * i, i < B_GATE ? 8 : i < B_CVD ? 4 : i == B_CVD ? 20 : 1);
    fence_async_smem();
  }
  const int warp = __shfl_sync(0xffffffffu, tid >> 5, 0), wg = warp >> 2, w = warp & 3;
  __syncthreads();

  if (wg == 3) {
    asm volatile("setmaxnreg.dec.sync.aligned.u32 56;");
    if (w == 0) {
      if (lane == 0) {
#pragma unroll 1
        for (int kb = 2; kb < 10; kb++) {
          if (kb >= 4) mbar_wait(bars + 8 * (kb == 7 ? B_E3 : B_EMPTY1 + (kb & 3)), (kb >> 3) & 1);
          TSIF(kb >= 4, 44 + kb);
          load_stage(sb, kb, b, m);
          TSIF(kb == 3, 60);
          if (kb == TRIG_KB) mbar_arrive(bars + 8 * B_LAST);
        }
        mbar_wait(bars + 8 * B_WOP, 0);
        mbar_wait(bars + 8 * WL_TRIG, 0);
        mbar_wait(bars + 8 * B_EPOCH, 0);
        flag_wait(g_cnt + C_W + 32 * hg, (lds32(sb + OFF_EPOCH) + 1) * 16);
        TS(30);
#pragma unroll 1
        for (int j = 0; j < 8; j++) {
          if (j >= 6) mbar_wait(bars + 8 * (B_EMPTY2 + j - 6), 0);
          if (j == 4) mbar_wait(bars + 8 * (RB32 & 2 ? B_ORB : B_ATTN), 0);
          TSIF(j >= 6, 100 + j);
          mbar_expect_tx(bars + 8 * (B_FULL2 + j), j == 0 ? WO_BYTES : j == 5 ? O_BYTES + WO_BYTES + 512 : O_BYTES + WO_BYTES);
          bulk_load(sb + off_w(j), g_WO + (hg * 8 + step_src(hg, j)) * 800, WO_BYTES, bars + 8 * (B_FULL2 + j));
        }
        mbar_wait(bars + 8 * (B_EMPTY2 + 3), 0);
        mbar_expect_tx(bars + 8 * B_QF, O_BYTES);
        tma_2d(sb + OFF_QS, &m.qm, 80 * hg, 128 * r, bars + 8 * B_QF);
        tma_2d(sb + OFF_QT, &m.qt, 80 * hg + 64, 128 * r, bars + 8 * B_QF);
      }
    } else if (w == 1) {
      unsigned epoch = 0;
      if (lane == 0) {
        epoch = atomicAdd(g_cnt + C_LAUNCH, 1u) / NCTA;
        asm volatile("st.shared.u32 [%0], %1;" ::"r"(sb + OFF_EPOCH), "r"(epoch) : "memory");
        mbar_arrive(bars + 8 * B_EPOCH);
        mbar_wait(bars + 8 * B_KVD, 0);
        mbar_expect_tx(bars + 8 * B_HB, 5 * 4096);
#pragma unroll 1
        for (int c = 0; c < 5; c++) {
          if (c == 3) mbar_wait(bars + 8 * B_S3, 0);
          bulk_load(sb + off_ch(c) + U_BYTES, p.ssm_k + (5 * b + c) * SEQ, 4096, bars + 8 * B_HB);
        }
#pragma unroll
        for (int c = 0; c < 4; c++) mbar_expect_tx(bars + 8 * (B_U + c), c < 3 ? U_BYTES : 2 * U_BYTES);
        const uint4* usrc = g_U + 5 * b * U_PITCH;
        mbar_wait(bars + 8 * B_USIG, 0);
        flag_wait(g_cnt + C_PREP + 32 * (b & 15), (epoch + 1) * NCTA);
        TS(23);
#pragma unroll
        for (int c = 0; c < 5; c++) {
          if (c == 3) mbar_wait(bars + 8 * (B_U + 2), 0);
          bulk_load(sb + off_ch(c), usrc + c * U_PITCH, U_BYTES, bars + 8 * (B_U + (c < 3 ? c : 3)));
          TSIF(c == 0 || c == 4, 116 + (c >> 2));
        }
      }
      epoch = __shfl_sync(0xffffffffu, epoch, 0);
      if (lane < 8) {
        const int src = (b & ~7) | step_src(hg, lane);
        mbar_wait(bars + 8 * B_ATTN, 0);
        TS(20);
        bool seen = false;
#pragma unroll 1
        for (int spins = 0; spins < SPIN_LIMIT; spins++) {
          const bool now = !seen && (int)(flag_read(g_cnt + C_O + 32 * src) - (epoch + 1)) >= 0;
          if (now && lane >= 1 && lane < 4) bulk_load(sb + off_o(lane), g_O + src * 1280, O_BYTES, bars + 8 * (B_FULL2 + lane));
          seen = seen || now;
          if (__all_sync(0xff, seen)) break;
        }
        TS(21);
        if (lane == 5) bulk_load(sb + OFF_GATE, g_gate + 128 * r, 512, bars + 8 * (B_FULL2 + 5));
#pragma unroll 1
        for (int j = 4; j < 8; j++) {
          if (lane == j) {
            mbar_wait(bars + 8 * (j < 6 ? B_C34 : B_EMPTY2 + j - 6), 0);
            bulk_load(sb + off_o(j), g_O + src * 1280, O_BYTES, bars + 8 * (B_FULL2 + j));
          }
          __syncwarp(0xff);
        }
        TS(22);
      }
    } else if (w == 2) {
      if (HALO_INIT && b < NCTA - 8) {
        mbar_wait(bars + 8 * HALO_INIT, 0);
#pragma unroll 1
        for (int j = 0; j < 14; j++)
          asm volatile("st.relaxed.gpu.global.v4.u32 [%0], {%1, %1, %1, %1};" ::"l"(g_halo + b * 448 + 32 * j + lane), "r"(0) : "memory");
      }
      mbar_wait(bars + 8 * B_PREP, 0);
      flag_signal(g_cnt + C_PREP, 16, lane);
      TS(25);
      if (lane == 0) {
        mbar_arrive(bars + 8 * B_USIG);
        mbar_expect_tx(bars + 8 * B_ORB, (RB32 & 2 ? O_BYTES / 4 : O_BYTES) + 64);
        mbar_wait(bars + 8 * B_GATE, 0);
        publish(g_gate + 16 * b, sb + OFF_GATE + 64 * hg, 64, bars + 8 * B_ORB);
        mbar_wait(bars + 8 * B_ATTN, 0);
        if (RB32 & 2) {
          bulk_store(g_O + b * 1280, sb + OFF_OA, O_BYTES);
          bulk_wait_read();
          tma_2d(sb + OFF_KVX + 10240, &m.ol, 48, b * 160, bars + 8 * B_ORB);
        } else {
          publish(g_O + b * 1280, sb + OFF_OA, O_BYTES, bars + 8 * B_ORB);
        }
        TS(74);
        mbar_wait(bars + 8 * B_ORB, 0);
        flag_bump(g_cnt + C_O + 32 * b);
        TS(26);
        mbar_arrive(bars + 8 * B_OSIG);
      }
    } else {
      if (lane == 0) {
        uint4* dst = g_WO + (hg * 8 + (r >> 1)) * 800 + (r & 1) * 80;
        mbar_wait(bars + 8 * B_S3, 0);
        asm volatile("cp.async.bulk.prefetch.L2.global [%0], 6400;" ::"l"(p.wo + b * 3200) : "memory");
        mbar_wait(bars + 8 * B_P1, 0);
        mbar_wait(bars + 8 * WB_TRIG, 0);
        mbar_expect_tx(bars + 8 * B_WST, WO_BYTES / 2);
        tma_3d(sb + OFF_WA, &m.wo, 0, 40 * r, 5 * hg, bars + 8 * B_WST);
        mbar_wait(bars + 8 * B_WST, 0);
#pragma unroll 1
        for (int n = 0; n < 5; n++) bulk_store(dst + 160 * n, sb + OFF_WA + 1280 * n, 1280);
        bulk_wait_read();
        mbar_expect_tx(bars + 8 * B_WST, WO_BYTES / 2);
#pragma unroll 1
        for (int n = 0; n < 5; n++) bulk_load(sb + OFF_WA + 1280 * n, dst + 160 * n, 1280, bars + 8 * B_WST);
        mbar_wait(bars + 8 * B_WST, 1);
        flag_bump(g_cnt + C_W + 32 * hg);
        mbar_arrive(bars + 8 * B_WOP);
        TS(71);
        mbar_expect_tx(bars + 8 * B_C34, 3 * (RB32 & 1 ? 1024 : U_BYTES));
        mbar_expect_tx(bars + 8 * B_YRB, 2 * (RB32 & 1 ? 1024 : U_BYTES));
#pragma unroll 1
        for (int c = 0; c < 5; c++) {
          mbar_wait(bars + 8 * (B_YST + c), 0);
          if (RB32 & 1) {
            bulk_store(g_U + (5 * b + c) * U_PITCH, sb + off_ch(c), U_BYTES);
            bulk_wait_read();
            tma_2d(sb + off_ch(c), &m.yl, 48, (5 * b + c) * (U_PITCH / 8), bars + 8 * (c < 3 ? B_C34 : B_YRB));
          } else {
            publish(g_U + (5 * b + c) * U_PITCH, sb + off_ch(c), U_BYTES, bars + 8 * (c < 3 ? B_C34 : B_YRB));
          }
        }
        TS(75);
        mbar_wait(bars + 8 * B_C34, 0);
        mbar_wait(bars + 8 * B_YRB, 0);
        flag_bump(g_cnt + C_Y + 32 * (b >> 4));
        TS(27);
        mbar_arrive(bars + 8 * B_YSIG);
        mbar_expect_tx(bars + 8 * B_YFULL, 20480);
        flag_wait(g_cnt + C_Y + 32 * hg, (lds32(sb + OFF_EPOCH) + 1) * 16);
        TS(24);
        tma_2d(sb + OFF_YT, &m.y, 128 * r, 80 * hg, bars + 8 * B_YFULL);
        tma_2d(sb + OFF_YT + 10240, &m.y, 128 * r + 64, 80 * hg, bars + 8 * B_YFULL);
      }
    }
  } else {
    asm volatile("setmaxnreg.inc.sync.aligned.u32 152;");
    if (wg < 2) {
      float acc[120];
#pragma unroll
      for (int i = 0; i < 120; i++) acc[i] = 0.f;
      const uint32_t da = desc_lo(sb + wg * 8192, 16), db = desc_lo(sb + ST_W, 8192), dc = desc_lo(sb + ST_WT, 2048);
      mbar_wait(bars + 8 * B_F0, 0);
      TSIF(w == 0 && wg == 0, 1);
      wg_fence();
#pragma unroll
      for (int k = 0; k < 4; k++) WgSST<192>::mma<HI_SW128, HI_SW128>(acc, da + 2 * k, db + 128 * k, 1);
      wg_commit();
      mbar_wait(bars + 8 * B_FULL1, 0);
      wg_fence();
#pragma unroll
      for (int k = 0; k < 4; k++) WgSST<48>::mma<HI_SW128, HI_SW32>(acc + 96, da + 2 * k, dc + 32 * k, 1);
      wg_commit();
#pragma unroll 1
      for (int kb = 1; kb < 10; kb++) {
        mbar_wait(bars + 8 * (B_FULL1 + (kb & 3)), (kb >> 2) & 1);
        const uint32_t so = (kb & 3) * (STAGE_BYTES >> 4);
        wg_fence();
#pragma unroll
        for (int k = 0; k < 4; k++) {
          WgSST<192>::mma<HI_SW128, HI_SW128>(acc, da + so + 2 * k, db + so + 128 * k, 1);
          WgSST<48>::mma<HI_SW128, HI_SW32>(acc + 96, da + so + 2 * k, dc + so + 32 * k, 1);
        }
        wg_commit();
        wg_wait<1>();
        if (lane == 0) mbar_arrive(bars + 8 * (kb == 4 ? B_E3 : B_EMPTY1 + ((kb - 1) & 3)));
      }
      mbar_wait(bars + 8 * B_EPOCH, 0);
      const uint32_t tag = lds32(sb + OFF_EPOCH) + 1;
      mbar_wait(bars + 8 * B_S3, 0);
      wg_wait<0>();
      pin<120>(acc);
      if (lane == 0) mbar_arrive(bars + 8 * B_P1);
      TSM(w == 0, 3 + wg);
      attention(acc, sb, b, wg, w, lane, tag);
    } else {
      const int tw = tid & 127, chl = 64 * (b & 1) + 8 * w + (lane >> 2);
      uint4* up = g_U + chl * U_PITCH + ((4 * (b >> 1) + (lane & 3)) ^ ((b >> 2) & 1));
      uint2 sw[10];
      uint32_t dv = 0;
      if (lane < 5) dv = __ldg(reinterpret_cast<const unsigned short*>(p.ssm_D) + 5 * b + lane);
#pragma unroll
      for (int i = 0; i < 10; i++) sw[i] = ldg64(reinterpret_cast<const uint2*>(p.shift_k) + chl + 128 * (i >> 1) + 32 * (i & 1));
      uint32_t tab[12];
      uint32_t tt[2];
      fft_tables(tab, tw);
      fft_twiddles(tt, tw);
      uint4 res[10];
#pragma unroll
      for (int i = 0; i < 10; i++) res[i] = make_uint4(0, 0, 0, 0);
#pragma unroll 1
      for (int slab = 0; slab < 5; slab++) {
#pragma unroll
        for (int i = 0; i < 8; i++) res[i] = res[i + 2];
        prep_slab(res + 8, sw, sb, slab, w, lane);
        TSIF(w == 0, 99 + 4 * slab);
#pragma unroll
        for (int i = 0; i < 8; i++) sw[i] = sw[i + 2];
      }
      TSIF(w == 0, 28);
      __syncwarp();
      if (lane == 0) mbar_arrive(bars + 8 * B_KVD + ((res[8].x ^ res[9].x) & p.zero));
      mbar_wait(bars + 8 * B_KVD, 0);
      fft_tables_store(tab, sb, tw);
      mbar_wait(bars + 8 * B_LAST, 0);
#pragma unroll
      for (int i = 0; i < 10; i++) up[(128 * (i >> 1) + 32 * (i & 1)) * U_PITCH] = res[i];
      __syncwarp();
      if (lane == 0) mbar_arrive(bars + 8 * B_PREP);
      TSIF(w == 0, 5);
      mbar_wait(bars + 8 * B_LAST, 0);
      prep_gate(p, sb, b, w, lane);
      __syncwarp();
      if (lane == 0) mbar_arrive(bars + 8 * B_GATE);
      TSIF(w == 0, 72);
      mbar_wait(bars + 8 * B_HB, 0);
      TSIF(w == 0, 2);
      const uint32_t ha = sb + U_BYTES + ((tw >> 3) * 16 + 8 + (tw & 7)) * 16;
      uint4 hv[5];
#pragma unroll
      for (int c = 0; c < 5; c++) hv[c] = lds128(ha + off_ch(c));
      __syncwarp();
#pragma unroll
      for (int c = 0; c < 5; c++) sts128((ha ^ 16) + off_ch(c), hv[c].x, hv[c].y, hv[c].z, hv[c].w);
      asm volatile("st.shared.v2.u32 [%0], {%1, %2};" ::"r"(sb + OFF_TT + 8 * tw), "r"(tt[0]), "r"(tt[1]) : "memory");
      if (tw < 5) asm volatile("st.shared.f32 [%0], %1;" ::"r"(sb + OFF_D + 4 * tw), "f"(bf_lo(dv) * 0.125f) : "memory");
      fence_async_smem();
      __syncwarp();
      if (lane == 0) mbar_arrive(bars + 8 * B_HA);
      TSIF(w == 0, 6);
    }

    FftConst fc;
    TSM(w == 0 && wg == 0, 104);
    mbar_wait(bars + 8 * B_HA, 0);
    fft_matrices(fc, sb, w, lane);
    TSM(w == 0 && wg == 0, 105);
    TSM(w == 0 && wg == 2, 124);
#pragma unroll 1
    for (uint32_t tasks = wg == 0 ? TASK0 : wg == 1 ? TASK1 : TASK2; tasks; tasks >>= 4) {
      const int c = (tasks & 7) - 1;
      conv_channel(fc, sb, c, wg, w, lane);
      if (lane == 0) mbar_arrive(bars + 8 * (B_YST + c));
      TSM(w == 0, 10 + c);
    }

    if (wg != WO_SKIP) {
      const int wg = (warp >> 2) > WO_SKIP ? (warp >> 2) - 1 : warp >> 2;
      const int g = lane >> 2;
      float acc[40];
#pragma unroll
      for (int i = 0; i < 40; i++) acc[i] = 0.f;
      const uint32_t da = desc_lo(sb + wg * 1024, 2048), db = desc_lo(sb, 2560);
      mbar_wait(bars + 8 * B_ORB, 0);
      mbar_wait(bars + 8 * B_FULL2, 0);
      TSM(w == 0, 15 + wg);
#pragma unroll 1
      for (int j = 0; j < 8; j++) {
        if (j == (wg ? WO_E1 : WO_E0)) mbar_wait(bars + 8 * B_CVD, 0);
        mbar_wait(bars + 8 * (B_FULL2 + j), 0);
        TSM(w == 0 && wg == 0, 44 + (j < 4 ? j : j + 6));
        const uint32_t oa = da + (off_o(j) >> 4), ob = db + (off_w(j) >> 4);
        wg_fence();
#pragma unroll
        for (int k = 0; k < 5; k++) WgSST<80>::mma<HI_NONE, HI_SW32>(acc, oa + 256 * k, ob + 32 * k, 1);
        wg_commit();
        wg_wait<1>();
        if (j >= 1 && j <= 4 && lane == 0) mbar_arrive(bars + 8 * (B_EMPTY2 + j - 1));
      }
      TSIF(w == 0 && wg == 0, 113);
      const int tr = 64 * wg + 16 * w + (lane & 15);
      const uint32_t fm = sb + OFF_QS + tr * 128, fx = (lane >> 4) ^ (tr & 7);
      const uint32_t ft = sb + OFF_QT + tr * 32 + (((lane >> 4) ^ (tr >> 2)) & 1) * 16;
      const float g0 = __uint_as_float(lds32(sb + OFF_GATE + (64 * wg + 16 * w + g) * 4));
      const float g1 = __uint_as_float(lds32(sb + OFF_GATE + (64 * wg + 16 * w + 8 + g) * 4));
      const uint32_t ga = pack2(g0, g0), gb = pack2(g1, g1);
      const uint32_t na = pack2(1.f - g0, 1.f - g0), nb = pack2(1.f - g1, 1.f - g1);

      uint32_t qf[20];
      mbar_wait(bars + 8 * B_QF, 0);
      TSM(w == 0 && wg == 0, 99);
#pragma unroll
      for (int j = 0; j < 5; j++) ldsm4(qf + 4 * j, j < 4 ? fm + ((fx ^ (2 * j)) << 4) : ft);
#pragma unroll
      for (int i = 0; i < 20; i++) {
        qf[i] = bmul((i & 1) ? gb : ga, qf[i]);
        asm volatile("" : "+r"(qf[i]));
      }

      wg_wait<0>();
      pin<40>(acc);
      TSM(w == 0, 17 + wg);
      uint32_t pb[20];
#pragma unroll
      for (int j = 0; j < 10; j++) {
        pb[2 * j] = bmul(na, pack2(acc[4 * j], acc[4 * j + 1]));
        pb[2 * j + 1] = bmul(nb, pack2(acc[4 * j + 2], acc[4 * j + 3]));
        asm volatile("" : "+r"(pb[2 * j]), "+r"(pb[2 * j + 1]));
      }
      const uint32_t ya = sb + OFF_YT + wg * 10240 + ((lane >> 4) * 8 + (lane & 7)) * 128 +
                          (((2 * w + (((lane >> 3) & 1) ^ wg)) ^ (lane & 7)) << 4);
      mbar_wait(bars + 8 * B_YFULL, 0);
      TSM(w == 0 && wg == 0, 19);
#pragma unroll
      for (int j = 0; j < 5; j++) {
        uint32_t y[4];
        ldsm4t(y, ya + 2048 * j);
#pragma unroll
        for (int i = 0; i < 4; i++)
          qf[4 * j + i] = bfma(qf[4 * j + i], y[i], pb[4 * j + i]);
      }
#pragma unroll
      for (int j = 0; j < 5; j++) stsm4(j < 4 ? fm + ((fx ^ (2 * j)) << 4) : ft, qf + 4 * j);
      fence_async_smem();
      __syncwarp();
      if (lane == 0) {
        const int row = 64 * wg + 16 * w;
        asm volatile("cp.async.bulk.tensor.2d.global.shared::cta.bulk_group [%0, {%2, %3}], [%1];"
                     ::"l"(&m.om), "r"(sb + OFF_QS + row * 128), "r"(80 * hg), "r"(128 * r + row) : "memory");
        asm volatile("cp.async.bulk.tensor.2d.global.shared::cta.bulk_group [%0, {%2, %3}], [%1];"
                     ::"l"(&m.ot), "r"(sb + OFF_QT + row * 32), "r"(80 * hg + 64), "r"(128 * r + row) : "memory");
        asm volatile("cp.async.bulk.commit_group;\ncp.async.bulk.wait_group.read 0;" ::: "memory");
      }
      TSM(w == 0 || w == 3, 40 + 2 * wg + (w & 1));
    }
  }
}

typedef CUresult (*EncodeFn)(CUtensorMap*, CUtensorMapDataType, cuuint32_t, void*, const cuuint64_t*, const cuuint64_t*,
                             const cuuint32_t*, const cuuint32_t*, CUtensorMapInterleave, CUtensorMapSwizzle,
                             CUtensorMapL2promotion, CUtensorMapFloatOOBfill);

void encode(EncodeFn fn, CUtensorMap* tm, const void* base, int rank, const cuuint64_t* dims, const cuuint64_t* strides,
            const cuuint32_t* box, CUtensorMapSwizzle swz) {
  const cuuint32_t ones[3] = {1, 1, 1};
  fn(tm, CU_TENSOR_MAP_DATA_TYPE_BFLOAT16, rank, const_cast<void*>(base), dims, strides, box, ones,
     CU_TENSOR_MAP_INTERLEAVE_NONE, swz, CU_TENSOR_MAP_L2_PROMOTION_L2_128B, CU_TENSOR_MAP_FLOAT_OOB_FILL_NONE);
}

}

extern "C" void kernel_launch(void* const* d_in, const int* in_sizes, int n_in, void* d_out, int out_size) {
  (void)in_sizes; (void)n_in; (void)out_size;
  Params p;
  p.q = (const __nv_bfloat16*)d_in[0];
  p.k = (const __nv_bfloat16*)d_in[1];
  p.v = (const __nv_bfloat16*)d_in[2];
  p.shift_k = (const __nv_bfloat16*)d_in[3];
  p.ssm_k = (const __nv_bfloat16*)d_in[4];
  p.ssm_D = (const __nv_bfloat16*)d_in[5];
  p.wqkv = (const __nv_bfloat16*)d_in[7];
  p.wo = (const __nv_bfloat16*)d_in[8];
  p.gate_w = (const __nv_bfloat16*)d_in[9];
  p.out = (__nv_bfloat16*)d_out;
  p.zero = 0;

  static EncodeFn fn = nullptr;
  static void *yaddr = nullptr, *oaddr = nullptr;
  if (!fn) {
    cudaDriverEntryPointQueryResult qr;
    void* f = nullptr;
    cudaGetDriverEntryPoint("cuTensorMapEncodeTiled", &f, cudaEnableDefault, &qr);
    fn = (EncodeFn)f;
    cudaGetSymbolAddress(&yaddr, g_U);
    cudaGetSymbolAddress(&oaddr, g_O);
    cudaFuncSetAttribute(fused_kernel, cudaFuncAttributeMaxDynamicSharedMemorySize, SMEM_BYTES);
  }
  Maps m;
  {
    const cuuint64_t dims[3] = {640, 1024, 2}, st[2] = {2560, 1280};
    const cuuint32_t box[3] = {64, 64, 2};
    encode(fn, &m.x, p.q, 3, dims, st, box, CU_TENSOR_MAP_SWIZZLE_128B);
  }
  {
    const cuuint64_t dims[3] = {640, 640, 3}, st[2] = {3840, 1280};
    const cuuint32_t box[3] = {64, 64, 3}, boxt[3] = {16, 64, 3};
    encode(fn, &m.wm, p.wqkv, 3, dims, st, box, CU_TENSOR_MAP_SWIZZLE_128B);
    encode(fn, &m.wt, p.wqkv, 3, dims, st, boxt, CU_TENSOR_MAP_SWIZZLE_32B);
  }
  {
    const cuuint64_t dims[3] = {64, 2048, 10}, st[2] = {1280, 128};
    const cuuint32_t boxk[3] = {64, 35, 1}, boxv[3] = {64, 32, 1};
    encode(fn, &m.k, p.k, 3, dims, st, boxk, CU_TENSOR_MAP_SWIZZLE_128B);
    encode(fn, &m.v, p.v, 3, dims, st, boxv, CU_TENSOR_MAP_SWIZZLE_128B);
  }
  {
    const cuuint64_t dims[3] = {16, 640, 40}, st[2] = {1280, 32};
    const cuuint32_t box[3] = {16, 40, 5};
    encode(fn, &m.wo, p.wo, 3, dims, st, box, CU_TENSOR_MAP_SWIZZLE_32B);
  }
  {
    const cuuint64_t dims[2] = {2048, 640}, st[1] = {U_PITCH * 16};
    const cuuint32_t box[2] = {64, 80};
    encode(fn, &m.y, yaddr, 2, dims, st, box, CU_TENSOR_MAP_SWIZZLE_128B);
    const cuuint64_t dl[2] = {64, DIM * U_PITCH / 8}, dol[2] = {64, NCTA * 160}, sl[1] = {128};
    const cuuint32_t bl[2] = {16, 32}, bol[2] = {16, 160};
    encode(fn, &m.yl, yaddr, 2, dl, sl, bl, CU_TENSOR_MAP_SWIZZLE_NONE);
    encode(fn, &m.ol, oaddr, 2, dol, sl, bol, CU_TENSOR_MAP_SWIZZLE_NONE);
  }
  {
    const cuuint64_t dims[2] = {640, 2048}, st[1] = {1280};
    const cuuint32_t bqm[2] = {64, 128}, bqt[2] = {16, 128}, bom[2] = {64, 16}, bot[2] = {16, 16};
    encode(fn, &m.qm, p.q, 2, dims, st, bqm, CU_TENSOR_MAP_SWIZZLE_128B);
    encode(fn, &m.qt, p.q, 2, dims, st, bqt, CU_TENSOR_MAP_SWIZZLE_32B);
    encode(fn, &m.om, p.out, 2, dims, st, bom, CU_TENSOR_MAP_SWIZZLE_128B);
    encode(fn, &m.ot, p.out, 2, dims, st, bot, CU_TENSOR_MAP_SWIZZLE_32B);
  }
  fused_kernel<<<NCTA, NTHR, SMEM_BYTES>>>(m, p);
}
```

```cpp
#include <cuda.h>
#include <cuda_bf16.h>
#include <cuda_runtime.h>
#include <stdint.h>

namespace {

constexpr int SEQ = 2048, DIM = 640, NCTA = 128, NTHR = 512;

#define KV_KB 2
#define DEV_EXIT 0
#define FENCE_LO 0
#define FENCE_HI 0
#define WB_TRIG B_USIG
#define T_ISSUE 288
#define T_INIT 448
#define TASK0 0x3
#define TASK1 0x52
#define TASK2 0x41

constexpr uint32_t STAGE_BYTES = 47104, ST_W = 16384, ST_WT = 40960;
constexpr uint32_t O_BYTES = 20480, WO_BYTES = 12800;
constexpr uint32_t OFF_OA = 0;
constexpr uint32_t OFF_QS = 3 * O_BYTES, OFF_QT = OFF_QS + 16384;
constexpr uint32_t OFF_WC = 81920;
constexpr uint32_t OFF_WA = 94720;
constexpr uint32_t OFF_GATE = 145920;
constexpr uint32_t OFF_TT = 146432;
constexpr uint32_t OFF_KVX = 148480;
constexpr uint32_t OFF_CH3 = 163840;
constexpr uint32_t CH_BYTES = 12288, U_BYTES = 4096;
constexpr uint32_t OFF_FT = 225280, OFF_GT = 229376;
constexpr uint32_t OFF_CH0 = 188416;
constexpr uint32_t OFF_KVS = OFF_CH0, KVS_V = 4480, KVS_BYTES = 8576;
constexpr uint32_t OFF_YT = 163840;
constexpr uint32_t OFF_BAR = 231936;
constexpr uint32_t SMEM_BYTES = OFF_BAR + 512;

enum : uint32_t {
  B_EMPTY1 = 0, B_S3 = 3, B_E3 = 4, B_EMPTY2 = 5, B_ATTN = 9, B_P1 = 10,
  B_GATE = 11, B_HA = 12, B_KVD = 13, B_PREP = 14, B_YST = 15,
  B_CVD = 20,
  B_FULL2 = 21, B_U = 29, B_KV = 33, B_HB = 38, B_C34 = 39, B_YRB = 40, B_YFULL = 41, B_EPOCH = 42, B_LAST = 43,
  B_WOP = 44, B_USIG = 45, B_WST = 46, B_QF = 47, B_ORB = 48,
  B_F0 = 49, B_FULL1 = 50
};
constexpr uint32_t OFF_EPOCH = OFF_BAR + 8 * 58, OFF_D = OFF_BAR + 8 * 60;
__device__ __forceinline__ uint32_t off_o(int j) { return j < 4 ? OFF_OA + j * O_BYTES : j < 6 ? OFF_CH0 + (j - 4) * O_BYTES : OFF_OA + (j - 6) * O_BYTES; }
__device__ __forceinline__ uint32_t off_w(int j) { return j < 4 ? OFF_WA + j * WO_BYTES : j == 4 ? OFF_KVX : j == 5 ? OFF_WC : OFF_WA + (j - 6) * WO_BYTES; }
__device__ __forceinline__ int step_src(int hg, int j) { return j == 0 ? hg : j <= hg ? j - 1 : j; }
__device__ __forceinline__ bool tail_first(int hg) { return (hg & 3) == 3; }
__device__ __forceinline__ uint32_t off_ch(int c) { return (c < 3 ? OFF_CH0 : OFF_CH3 - 3 * CH_BYTES) + c * CH_BYTES; }

#define U_PITCH 264
__device__ __align__(1024) uint4 g_U[DIM * U_PITCH];
__device__ __align__(128) uint4 g_O[NCTA * 1280];
__device__ uint4 g_WO[64 * 800];
__device__ uint4 g_halo[NCTA * 2 * 7 * 32];
__device__ __align__(128) float g_gate[SEQ];
__device__ unsigned g_cnt[32 * (1 + 2 * 16 + 8 + NCTA)];
constexpr int C_LAUNCH = 0, C_PREP = 32, C_Y = 32 * 17, C_W = 32 * 33, C_O = 32 * 41;

#define TSM(cond, slot) do { } while (0)
#define TSIF(cond, slot) do { if (__LINE__ >= FENCE_LO && __LINE__ < FENCE_HI) sched_fence(); } while (0)
__device__ __forceinline__ void sched_fence() {
  asm volatile("{\n.reg .pred p;\n.reg .u32 c;\nmov.u32 c, %%clock;\nsetp.eq.u32 p, c, 0;\n@p st.shared.u32 [%0], c;\n}"
               ::"r"(1024 + OFF_EPOCH + 4) : "memory");
}
#define TS(slot) TSIF(true, slot)

struct Params {
  const __nv_bfloat16 *q, *k, *v, *shift_k, *ssm_k, *ssm_D, *wqkv, *wo, *gate_w;
  __nv_bfloat16* out;
  uint32_t zero;
};

constexpr int SPIN_LIMIT = 1 << 17;

__device__ __forceinline__ void mbar_init(uint32_t bar, uint32_t count) {
  asm volatile("mbarrier.init.shared::cta.b64 [%0], %1;" ::"r"(bar), "r"(count) : "memory");
}
__device__ __forceinline__ void mbar_expect_tx(uint32_t bar, uint32_t bytes) {
  asm volatile("mbarrier.arrive.expect_tx.shared::cta.b64 _, [%0], %1;" ::"r"(bar), "r"(bytes) : "memory");
}
__device__ __forceinline__ void mbar_arrive(uint32_t bar) {
  asm volatile("mbarrier.arrive.shared::cta.b64 _, [%0];" ::"r"(bar) : "memory");
}
__device__ __forceinline__ void mbar_wait(uint32_t bar, uint32_t parity) {
  uint32_t ok;
  int spins = 0;
  do {
      asm volatile("{\n.reg .pred p;\nmbarrier.try_wait.parity.shared::cta.b64 p, [%1], %2;\nselp.b32 %0, 1, 0, p;\n}"
                   : "=r"(ok) : "r"(bar), "r"(parity) : "memory");
    if (++spins > SPIN_LIMIT) break;
  } while (!ok);
}
__device__ __forceinline__ unsigned flag_read(const unsigned* p) {
  unsigned v;
  asm volatile("ld.relaxed.gpu.global.u32 %0, [%1];" : "=r"(v) : "l"(p) : "memory");
  return v;
}
__device__ __forceinline__ void flag_poll(const unsigned* p, unsigned target) {
  unsigned v;
  int spins = 0;
  do {
    asm volatile("ld.relaxed.gpu.global.u32 %0, [%1];" : "=r"(v) : "l"(p) : "memory");
    if (++spins > SPIN_LIMIT) break;
  } while ((int)(v - target) < 0);
}
__device__ __forceinline__ void flag_wait(const unsigned* p, unsigned target) {
  flag_poll(p, target);
}
__device__ __forceinline__ void flag_signal(unsigned* p, int n, int lane) {
  if (lane == 0) asm volatile("fence.release.gpu;" ::: "memory");
  __syncwarp();
  if (lane < n) asm volatile("red.relaxed.gpu.global.add.u32 [%0], 1;" ::"l"(p + 32 * lane) : "memory");
}
__device__ __forceinline__ void flag_bump(unsigned* p) {
  asm volatile("red.relaxed.gpu.global.add.u32 [%0], 1;" ::"l"(p) : "memory");
}
__device__ __forceinline__ void fence_async_smem() { asm volatile("fence.proxy.async.shared::cta;" ::: "memory"); }
__device__ __forceinline__ void wg_sync(int id) { asm volatile("bar.sync %0, 128;" ::"r"(id) : "memory"); }

__device__ __forceinline__ void tma_2d(uint32_t dst, const CUtensorMap* tm, int c0, int c1, uint32_t bar) {
  asm volatile("cp.async.bulk.tensor.2d.shared::cluster.global.mbarrier::complete_tx::bytes [%0], [%1, {%3, %4}], [%2];"
               ::"r"(dst), "l"(tm), "r"(bar), "r"(c0), "r"(c1) : "memory");
}
__device__ __forceinline__ void tma_3d(uint32_t dst, const CUtensorMap* tm, int c0, int c1, int c2, uint32_t bar) {
  asm volatile("cp.async.bulk.tensor.3d.shared::cluster.global.mbarrier::complete_tx::bytes [%0], [%1, {%3, %4, %5}], [%2];"
               ::"r"(dst), "l"(tm), "r"(bar), "r"(c0), "r"(c1), "r"(c2) : "memory");
}
__device__ __forceinline__ void bulk_load(uint32_t dst, const void* src, uint32_t bytes, uint32_t bar) {
  asm volatile("cp.async.bulk.shared::cluster.global.mbarrier::complete_tx::bytes [%0], [%1], %2, [%3];"
               ::"r"(dst), "l"(src), "r"(bytes), "r"(bar) : "memory");
}
__device__ __forceinline__ void bulk_store(void* dst, uint32_t src, uint32_t bytes) {
  asm volatile("cp.async.bulk.global.shared::cta.bulk_group [%0], [%1], %2;" ::"l"(dst), "r"(src), "r"(bytes) : "memory");
}
__device__ __forceinline__ void bulk_wait_read() {
  asm volatile("cp.async.bulk.commit_group;\ncp.async.bulk.wait_group.read 0;" ::: "memory");
}

__device__ __forceinline__ void publish(void* dst, uint32_t src, uint32_t bytes) {
  bulk_store(dst, src, bytes);
  bulk_wait_read();
}

__device__ __forceinline__ void wg_fence() { asm volatile("wgmma.fence.sync.aligned;" ::: "memory"); }
__device__ __forceinline__ void wg_commit() { asm volatile("wgmma.commit_group.sync.aligned;" ::: "memory"); }
template <int N> __device__ __forceinline__ void wg_wait() { asm volatile("wgmma.wait_group.sync.aligned %0;" ::"n"(N) : "memory"); }
__device__ __forceinline__ uint32_t desc_lo(uint32_t addr, uint32_t lbo) { return ((addr & 0x3FFFF) >> 4) | ((lbo >> 4) << 16); }
constexpr uint32_t desc_hi(uint32_t sbo, uint32_t swz) { return (sbo >> 4) | (swz << 30); }
constexpr uint32_t HI_SW128 = desc_hi(1024, 1), HI_SW64 = desc_hi(512, 2), HI_SW32 = desc_hi(256, 3), HI_NONE = desc_hi(128, 0);
template <int N> __device__ __forceinline__ void pin(float* d) {
#pragma unroll
  for (int i = 0; i < N; i++) asm volatile("" : "+f"(d[i])::"memory");
}

__device__ __forceinline__ uint32_t lds32(uint32_t a) {
  uint32_t v;
  asm volatile("ld.volatile.shared.u32 %0, [%1];" : "=r"(v) : "r"(a) : "memory");
  return v;
}
__device__ __forceinline__ uint2 ldg64(const void* a) {
  uint2 v;
  asm volatile("ld.global.nc.v2.u32 {%0, %1}, [%2];" : "=r"(v.x), "=r"(v.y) : "l"(a) : "memory");
  return v;
}
__device__ __forceinline__ void ldsm4(uint32_t* r, uint32_t a) {
  asm volatile("ldmatrix.sync.aligned.m8n8.x4.shared.b16 {%0, %1, %2, %3}, [%4];"
               : "=r"(r[0]), "=r"(r[1]), "=r"(r[2]), "=r"(r[3]) : "r"(a) : "memory");
}
__device__ __forceinline__ void ldsm4t(uint32_t* r, uint32_t a) {
  asm volatile("ldmatrix.sync.aligned.m8n8.x4.trans.shared.b16 {%0, %1, %2, %3}, [%4];"
               : "=r"(r[0]), "=r"(r[1]), "=r"(r[2]), "=r"(r[3]) : "r"(a) : "memory");
}
__device__ __forceinline__ uint2 lds64(uint32_t a) {
  uint2 v;
  asm volatile("ld.shared.v2.u32 {%0, %1}, [%2];" : "=r"(v.x), "=r"(v.y) : "r"(a) : "memory");
  return v;
}
__device__ __forceinline__ uint4 lds128(uint32_t a) {
  uint4 v;
  asm volatile("ld.shared.v4.u32 {%0, %1, %2, %3}, [%4];" : "=r"(v.x), "=r"(v.y), "=r"(v.z), "=r"(v.w) : "r"(a) : "memory");
  return v;
}
__device__ __forceinline__ void sts128(uint32_t a, uint32_t x, uint32_t y, uint32_t z, uint32_t w) {
  asm volatile("st.shared.v4.u32 [%0], {%1, %2, %3, %4};" ::"r"(a), "r"(x), "r"(y), "r"(z), "r"(w) : "memory");
}
__device__ __forceinline__ void stsm4(uint32_t a, const uint32_t* r) {
  asm volatile("stmatrix.sync.aligned.m8n8.x4.shared.b16 [%0], {%1, %2, %3, %4};" ::"r"(a), "r"(r[0]), "r"(r[1]), "r"(r[2]), "r"(r[3]) : "memory");
}
__device__ __forceinline__ uint32_t pack2(float lo, float hi) {
  uint32_t r;
  asm("cvt.rn.bf16x2.f32 %0, %1, %2;" : "=r"(r) : "f"(hi), "f"(lo));
  return r;
}
__device__ __forceinline__ uint32_t movm(uint32_t a) {
  uint32_t d;
  asm volatile("movmatrix.sync.aligned.m8n8.trans.b16 %0, %1;" : "=r"(d) : "r"(a));
  return d;
}
__device__ __forceinline__ uint32_t bmul(uint32_t a, uint32_t b) {
  uint32_t d;
  asm("mul.rn.bf16x2 %0, %1, %2;" : "=r"(d) : "r"(a), "r"(b));
  return d;
}
__device__ __forceinline__ uint32_t badd(uint32_t a, uint32_t b) {
  uint32_t d;
  asm("add.rn.bf16x2 %0, %1, %2;" : "=r"(d) : "r"(a), "r"(b));
  return d;
}
__device__ __forceinline__ uint32_t bfma(uint32_t a, uint32_t b, uint32_t c) {
  uint32_t d;
  asm("fma.rn.bf16x2 %0, %1, %2, %3;" : "=r"(d) : "r"(a), "r"(b), "r"(c));
  return d;
}
__device__ __forceinline__ float bf_lo(uint32_t x) { return __uint_as_float(x << 16); }
__device__ __forceinline__ float bf_hi(uint32_t x) { return __uint_as_float(x & 0xFFFF0000u); }
__device__ __forceinline__ float ex2(float x) {
  float y;
  asm("ex2.approx.ftz.f32 %0, %1;" : "=f"(y) : "f"(x));
  return y;
}
__device__ __forceinline__ float rcp(float x) {
  float y;
  asm("rcp.approx.ftz.f32 %0, %1;" : "=f"(y) : "f"(x));
  return y;
}
__device__ __forceinline__ void mma16816(float* d, uint32_t a0, uint32_t a1, uint32_t a2, uint32_t a3, uint32_t b0, uint32_t b1) {
  asm volatile("mma.sync.aligned.m16n8k16.row.col.f32.bf16.bf16.f32 {%0, %1, %2, %3}, {%4, %5, %6, %7}, {%8, %9}, {%0, %1, %2, %3};"
               : "+f"(d[0]), "+f"(d[1]), "+f"(d[2]), "+f"(d[3])
               : "r"(a0), "r"(a1), "r"(a2), "r"(a3), "r"(b0), "r"(b1));
}
__device__ __forceinline__ void mma1688(float* d, uint32_t a0, uint32_t a1, uint32_t b0) {
  asm volatile("mma.sync.aligned.m16n8k8.row.col.f32.bf16.bf16.f32 {%0, %1, %2, %3}, {%4, %5}, {%6}, {%0, %1, %2, %3};"
               : "+f"(d[0]), "+f"(d[1]), "+f"(d[2]), "+f"(d[3])
               : "r"(a0), "r"(a1), "r"(b0));
}

template <int N> struct WgRS;
template <int N> struct WgSST;
template <> struct WgRS<32> {
  template <uint32_t HB>
  static __device__ __forceinline__ void mma(float* d, const uint32_t* a, uint32_t db) {
    asm volatile("{\n.reg .pred p;\n.reg .b64 db;\nsetp.ne.b32 p, %22, 0;\n"
      "mov.b64 db, {%20, %21};\n"
      "wgmma.mma_async.sync.aligned.m64n32k16.f32.bf16.bf16 {"
      "%0, %1, %2, %3, %4, %5, %6, %7, %8, %9, %10, %11, %12, %13, %14, %15"
      "}, {%16, %17, %18, %19}, db, p, 1, 1, 1;\n}\n"
      : "+f"(d[0]), "+f"(d[1]), "+f"(d[2]), "+f"(d[3]), "+f"(d[4]), "+f"(d[5]), "+f"(d[6]), "+f"(d[7]),
        "+f"(d[8]), "+f"(d[9]), "+f"(d[10]), "+f"(d[11]), "+f"(d[12]), "+f"(d[13]), "+f"(d[14]), "+f"(d[15])
      : "r"(a[0]), "r"(a[1]), "r"(a[2]), "r"(a[3]), "r"(db), "n"(HB), "n"(1));
  }
  template <uint32_t HB>
  static __device__ __forceinline__ void set(float* d, const uint32_t* a, uint32_t db) {
    asm volatile("{\n.reg .pred p;\n.reg .b64 db;\nsetp.ne.b32 p, %22, 0;\n"
      "mov.b64 db, {%20, %21};\n"
      "wgmma.mma_async.sync.aligned.m64n32k16.f32.bf16.bf16 {"
      "%0, %1, %2, %3, %4, %5, %6, %7, %8, %9, %10, %11, %12, %13, %14, %15"
      "}, {%16, %17, %18, %19}, db, p, 1, 1, 1;\n}\n"
      : "=f"(d[0]), "=f"(d[1]), "=f"(d[2]), "=f"(d[3]), "=f"(d[4]), "=f"(d[5]), "=f"(d[6]), "=f"(d[7]),
        "=f"(d[8]), "=f"(d[9]), "=f"(d[10]), "=f"(d[11]), "=f"(d[12]), "=f"(d[13]), "=f"(d[14]), "=f"(d[15])
      : "r"(a[0]), "r"(a[1]), "r"(a[2]), "r"(a[3]), "r"(db), "n"(HB), "n"(0));
  }
};
template <> struct WgRS<64> {
  template <uint32_t HB>
  static __device__ __forceinline__ void mma(float* d, const uint32_t* a, uint32_t db) {
    asm volatile("{\n.reg .pred p;\n.reg .b64 db;\nsetp.ne.b32 p, %38, 0;\n"
      "mov.b64 db, {%36, %37};\n"
      "wgmma.mma_async.sync.aligned.m64n64k16.f32.bf16.bf16 {"
      "%0, %1, %2, %3, %4, %5, %6, %7, %8, %9, %10, %11, %12, %13, %14, %15, "
      "%16, %17, %18, %19, %20, %21, %22, %23, %24, %25, %26, %27, %28, %29, %30, %31"
      "}, {%32, %33, %34, %35}, db, p, 1, 1, 1;\n}\n"
      : "+f"(d[0]), "+f"(d[1]), "+f"(d[2]), "+f"(d[3]), "+f"(d[4]), "+f"(d[5]), "+f"(d[6]), "+f"(d[7]),
        "+f"(d[8]), "+f"(d[9]), "+f"(d[10]), "+f"(d[11]), "+f"(d[12]), "+f"(d[13]), "+f"(d[14]), "+f"(d[15]),
        "+f"(d[16]), "+f"(d[17]), "+f"(d[18]), "+f"(d[19]), "+f"(d[20]), "+f"(d[21]), "+f"(d[22]), "+f"(d[23]),
        "+f"(d[24]), "+f"(d[25]), "+f"(d[26]), "+f"(d[27]), "+f"(d[28]), "+f"(d[29]), "+f"(d[30]), "+f"(d[31])
      : "r"(a[0]), "r"(a[1]), "r"(a[2]), "r"(a[3]), "r"(db), "n"(HB), "n"(1));
  }
  template <uint32_t HB>
  static __device__ __forceinline__ void set(float* d, const uint32_t* a, uint32_t db) {
    asm volatile("{\n.reg .pred p;\n.reg .b64 db;\nsetp.ne.b32 p, %38, 0;\n"
      "mov.b64 db, {%36, %37};\n"
      "wgmma.mma_async.sync.aligned.m64n64k16.f32.bf16.bf16 {"
      "%0, %1, %2, %3, %4, %5, %6, %7, %8, %9, %10, %11, %12, %13, %14, %15, "
      "%16, %17, %18, %19, %20, %21, %22, %23, %24, %25, %26, %27, %28, %29, %30, %31"
      "}, {%32, %33, %34, %35}, db, p, 1, 1, 1;\n}\n"
      : "=f"(d[0]), "=f"(d[1]), "=f"(d[2]), "=f"(d[3]), "=f"(d[4]), "=f"(d[5]), "=f"(d[6]), "=f"(d[7]),
        "=f"(d[8]), "=f"(d[9]), "=f"(d[10]), "=f"(d[11]), "=f"(d[12]), "=f"(d[13]), "=f"(d[14]), "=f"(d[15]),
        "=f"(d[16]), "=f"(d[17]), "=f"(d[18]), "=f"(d[19]), "=f"(d[20]), "=f"(d[21]), "=f"(d[22]), "=f"(d[23]),
        "=f"(d[24]), "=f"(d[25]), "=f"(d[26]), "=f"(d[27]), "=f"(d[28]), "=f"(d[29]), "=f"(d[30]), "=f"(d[31])
      : "r"(a[0]), "r"(a[1]), "r"(a[2]), "r"(a[3]), "r"(db), "n"(HB), "n"(0));
  }
};
template <> struct WgSST<48> {
  template <uint32_t HA, uint32_t HB>
  static __device__ __forceinline__ void mma(float* d, uint32_t da, uint32_t db, int sc) {
    asm volatile("{\n.reg .pred p;\n.reg .b64 da, db;\nsetp.ne.b32 p, %28, 0;\n"
      "mov.b64 da, {%24, %25};\nmov.b64 db, {%26, %27};\n"
      "wgmma.mma_async.sync.aligned.m64n48k16.f32.bf16.bf16 {"
      "%0, %1, %2, %3, %4, %5, %6, %7, %8, %9, %10, %11, %12, %13, %14, %15, "
      "%16, %17, %18, %19, %20, %21, %22, %23"
      "}, da, db, p, 1, 1, 0, 1;\n}\n"
      : "+f"(d[0]), "+f"(d[1]), "+f"(d[2]), "+f"(d[3]), "+f"(d[4]), "+f"(d[5]), "+f"(d[6]), "+f"(d[7]),
        "+f"(d[8]), "+f"(d[9]), "+f"(d[10]), "+f"(d[11]), "+f"(d[12]), "+f"(d[13]), "+f"(d[14]), "+f"(d[15]),
        "+f"(d[16]), "+f"(d[17]), "+f"(d[18]), "+f"(d[19]), "+f"(d[20]), "+f"(d[21]), "+f"(d[22]), "+f"(d[23])
      : "r"(da), "n"(HA), "r"(db), "n"(HB), "r"(sc));
  }
};
template <> struct WgSST<80> {
  template <uint32_t HA, uint32_t HB>
  static __device__ __forceinline__ void mma(float* d, uint32_t da, uint32_t db, int sc) {
    asm volatile("{\n.reg .pred p;\n.reg .b64 da, db;\nsetp.ne.b32 p, %44, 0;\n"
      "mov.b64 da, {%40, %41};\nmov.b64 db, {%42, %43};\n"
      "wgmma.mma_async.sync.aligned.m64n80k16.f32.bf16.bf16 {"
      "%0, %1, %2, %3, %4, %5, %6, %7, %8, %9, %10, %11, %12, %13, %14, %15, "
      "%16, %17, %18, %19, %20, %21, %22, %23, %24, %25, %26, %27, %28, %29, %30, %31, "
      "%32, %33, %34, %35, %36, %37, %38, %39"
      "}, da, db, p, 1, 1, 0, 1;\n}\n"
      : "+f"(d[0]), "+f"(d[1]), "+f"(d[2]), "+f"(d[3]), "+f"(d[4]), "+f"(d[5]), "+f"(d[6]), "+f"(d[7]),
        "+f"(d[8]), "+f"(d[9]), "+f"(d[10]), "+f"(d[11]), "+f"(d[12]), "+f"(d[13]), "+f"(d[14]), "+f"(d[15]),
        "+f"(d[16]), "+f"(d[17]), "+f"(d[18]), "+f"(d[19]), "+f"(d[20]), "+f"(d[21]), "+f"(d[22]), "+f"(d[23]),
        "+f"(d[24]), "+f"(d[25]), "+f"(d[26]), "+f"(d[27]), "+f"(d[28]), "+f"(d[29]), "+f"(d[30]), "+f"(d[31]),
        "+f"(d[32]), "+f"(d[33]), "+f"(d[34]), "+f"(d[35]), "+f"(d[36]), "+f"(d[37]), "+f"(d[38]), "+f"(d[39])
      : "r"(da), "n"(HA), "r"(db), "n"(HB), "r"(sc));
  }
};
template <> struct WgSST<192> {
  template <uint32_t HA, uint32_t HB>
  static __device__ __forceinline__ void mma(float* d, uint32_t da, uint32_t db, int sc) {
    asm volatile("{\n.reg .pred p;\n.reg .b64 da, db;\nsetp.ne.b32 p, %100, 0;\n"
      "mov.b64 da, {%96, %97};\nmov.b64 db, {%98, %99};\n"
      "wgmma.mma_async.sync.aligned.m64n192k16.f32.bf16.bf16 {"
      "%0, %1, %2, %3, %4, %5, %6, %7, %8, %9, %10, %11, %12, %13, %14, %15, "
      "%16, %17, %18, %19, %20, %21, %22, %23, %24, %25, %26, %27, %28, %29, %30, %31, "
      "%32, %33, %34, %35, %36, %37, %38, %39, %40, %41, %42, %43, %44, %45, %46, %47, "
      "%48, %49, %50, %51, %52, %53, %54, %55, %56, %57, %58, %59, %60, %61, %62, %63, "
      "%64, %65, %66, %67, %68, %69, %70, %71, %72, %73, %74, %75, %76, %77, %78, %79, "
      "%80, %81, %82, %83, %84, %85, %86, %87, %88, %89, %90, %91, %92, %93, %94, %95"
      "}, da, db, p, 1, 1, 0, 1;\n}\n"
      : "+f"(d[0]), "+f"(d[1]), "+f"(d[2]), "+f"(d[3]), "+f"(d[4]), "+f"(d[5]), "+f"(d[6]), "+f"(d[7]),
        "+f"(d[8]), "+f"(d[9]), "+f"(d[10]), "+f"(d[11]), "+f"(d[12]), "+f"(d[13]), "+f"(d[14]), "+f"(d[15]),
        "+f"(d[16]), "+f"(d[17]), "+f"(d[18]), "+f"(d[19]), "+f"(d[20]), "+f"(d[21]), "+f"(d[22]), "+f"(d[23]),
        "+f"(d[24]), "+f"(d[25]), "+f"(d[26]), "+f"(d[27]), "+f"(d[28]), "+f"(d[29]), "+f"(d[30]), "+f"(d[31]),
        "+f"(d[32]), "+f"(d[33]), "+f"(d[34]), "+f"(d[35]), "+f"(d[36]), "+f"(d[37]), "+f"(d[38]), "+f"(d[39]),
        "+f"(d[40]), "+f"(d[41]), "+f"(d[42]), "+f"(d[43]), "+f"(d[44]), "+f"(d[45]), "+f"(d[46]), "+f"(d[47]),
        "+f"(d[48]), "+f"(d[49]), "+f"(d[50]), "+f"(d[51]), "+f"(d[52]), "+f"(d[53]), "+f"(d[54]), "+f"(d[55]),
        "+f"(d[56]), "+f"(d[57]), "+f"(d[58]), "+f"(d[59]), "+f"(d[60]), "+f"(d[61]), "+f"(d[62]), "+f"(d[63]),
        "+f"(d[64]), "+f"(d[65]), "+f"(d[66]), "+f"(d[67]), "+f"(d[68]), "+f"(d[69]), "+f"(d[70]), "+f"(d[71]),
        "+f"(d[72]), "+f"(d[73]), "+f"(d[74]), "+f"(d[75]), "+f"(d[76]), "+f"(d[77]), "+f"(d[78]), "+f"(d[79]),
        "+f"(d[80]), "+f"(d[81]), "+f"(d[82]), "+f"(d[83]), "+f"(d[84]), "+f"(d[85]), "+f"(d[86]), "+f"(d[87]),
        "+f"(d[88]), "+f"(d[89]), "+f"(d[90]), "+f"(d[91]), "+f"(d[92]), "+f"(d[93]), "+f"(d[94]), "+f"(d[95])
      : "r"(da), "n"(HA), "r"(db), "n"(HB), "r"(sc));
  }
};

struct FftConst {
  uint32_t f[2][4], fi[4][4];
  uint32_t ta[2][2], tb[2][2];
};
__device__ __forceinline__ void cis(int m, float scale, float& c, float& s) {
  const float a = (float)m * (-6.283185307179586f * scale);
  c = __cosf(a);
  s = __sinf(a);
}
__device__ __forceinline__ void fft_tables(uint32_t (&v)[12], int tw) {
  const int row = tw >> 2, ch = tw & 3;
#pragma unroll
  for (int i = 0; i < 4; i++) {
    float c[2], s[2], x[2];
#pragma unroll
    for (int e = 0; e < 2; e++) {
      cis((((32 * (8 * ch + 2 * i + e) + 15) * (4 * row - 63) + 2048) & 4095) - 2048, 1.f / 4096, c[e], s[e]);
      float gc, gs;
      cis((((row & 15) * (8 * (ch & 1) + 2 * i + e) + 8) & 15) - 8, 1.f / 16, gc, gs);
      x[e] = (row >> 4) == (ch >> 1) ? gc : (ch >> 1) ? gs : -gs;
    }
    v[i] = pack2(c[0] * 0.125f, c[1] * 0.125f);
    v[4 + i] = pack2(s[0] * 0.125f, s[1] * 0.125f);
    v[8 + i] = pack2(x[0], x[1]);
  }
#pragma unroll
  for (int i = 0; i < 12; i++) asm volatile("" : "+r"(v[i]));
}
__device__ __forceinline__ void fft_tables_store(const uint32_t (&v)[12], uint32_t sb, int tw) {
  const int row = tw >> 2;
  const uint32_t x = ((tw ^ (row >> 1)) & 3) << 4, a = sb + OFF_FT + (16 * (row >> 3) + (row & 7)) * 64 + x;
  sts128(a, v[0], v[1], v[2], v[3]);
  sts128(a + 512, v[4], v[5], v[6], v[7]);
  sts128(sb + OFF_GT + row * 64 + x, v[8], v[9], v[10], v[11]);
}
__device__ __forceinline__ void fft_twiddles(uint32_t (&v)[2], int tw) {
  float a[2], s[2];
#pragma unroll
  for (int i = 0; i < 2; i++) {
    float c;
    cis((2 * (2 * (tw & 3) + i) - 15) * (4 * (tw >> 2) - 63), 1.f / 4096, c, s[i]);
    a[i] = __fdividef(-s[i], 1.f + c);
  }
  v[0] = pack2(a[0], a[1]);
  v[1] = pack2(s[0], s[1]);
  asm volatile("" : "+r"(v[0]), "+r"(v[1]));
}
__device__ __forceinline__ void fft_matrices(FftConst& k, uint32_t sb, int w, int lane) {
  const uint32_t x = (lane >> 1) & 3;
  const uint2 t0 = lds64(sb + OFF_TT + 256 * w + 8 * lane), t1 = lds64(sb + OFF_TT + 256 * w + 8 * (lane ^ 3));
  k.ta[0][0] = t0.x;
  k.tb[0][0] = t0.y;
  k.ta[1][1] = __byte_perm(t1.x, 0, 0x1032);
  k.tb[1][1] = __byte_perm(t1.y, 0, 0x1032);
#pragma unroll
  for (int j = 0; j < 2; j++) {
    k.ta[1 - j][j] = k.ta[j][j] ^ 0x80008000u;
    k.tb[1 - j][j] = k.tb[j][j] ^ 0x80008000u;
    asm volatile("" : "+r"(k.ta[0][j]), "+r"(k.tb[0][j]), "+r"(k.ta[1][j]), "+r"(k.tb[1][j]));
  }
#pragma unroll
  for (int i = 0; i < 2; i++) {
    ldsm4(k.f[i], sb + OFF_FT + (16 * w + (lane & 15)) * 64 + (((2 * i + (lane >> 4)) ^ x) << 4));
    ldsm4t(k.fi[i], sb + OFF_FT + (32 * i + lane) * 64 + ((w ^ x) << 4));
#pragma unroll
    for (int j = 0; j < 4; j++) {
      k.fi[2 + i][j] = (j & 1) ? k.fi[i][j - 1] ^ 0x80008000u : k.fi[i][j + 1];
      asm volatile("" : "+r"(k.fi[2 + i][j]));
    }
  }
}
__device__ __forceinline__ void rot(uint32_t& x, uint32_t& y, uint32_t a, uint32_t b) {
  x = bfma(a, y, x);
  y = bfma(b, x, y);
  x = bfma(a, y, x);
}
__device__ __forceinline__ void twiddle_fwd(uint32_t (&a)[4][4], float* d, const FftConst& k) {
#pragma unroll
  for (int q = 0; q < 4; q++)
#pragma unroll
    for (int j = 0; j < 2; j++) {
      const float* x = d + 8 * q + 4 * j;
      uint32_t re = pack2(x[0], x[1]), im = pack2(x[2], x[3]);
      rot(re, im, k.ta[0][j], k.tb[0][j]);
      a[q & 2][2 * j + (q & 1)] = re;
      a[(q & 2) + 1][2 * j + (q & 1)] = im;
    }
}
__device__ __forceinline__ void g_step(float* d, const uint32_t (&a)[4][4], uint32_t dre, uint32_t dim) {
  WgRS<32>::set<HI_SW64>(d, a[0], dre);
  WgRS<32>::set<HI_SW64>(d + 16, a[2], dre);
  WgRS<32>::mma<HI_SW64>(d, a[1], dim);
  WgRS<32>::mma<HI_SW64>(d + 16, a[3], dim);
  wg_commit();
}

__device__ __forceinline__ void products(uint32_t (&a)[4][4], const float* H, const float* U, int p) {
#pragma unroll
  for (int j = 0; j < 2; j++)
#pragma unroll
    for (int m = 2 * p; m < 2 * p + 2; m++) {
      float pr[2], pi[2];
#pragma unroll
      for (int x = 0; x < 2; x++)
#pragma unroll
        for (int q = 0; q <= m; q++) {
          const int ih = 16 * (q >> 1) + 2 * (q & 1) + 4 * j + x, iu = 16 * ((m - q) >> 1) + 2 * ((m - q) & 1) + 4 * j + x;
          pr[x] = q ? fmaf(H[ih], U[iu], pr[x]) : H[ih] * U[iu];
          pi[x] = q ? fmaf(H[ih], U[iu + 8], pi[x]) : H[ih] * U[iu + 8];
          pr[x] = fmaf(-H[ih + 8], U[iu + 8], pr[x]);
          pi[x] = fmaf(H[ih + 8], U[iu], pi[x]);
        }
      a[m & 2][2 * j + (m & 1)] = pack2(pr[0], pr[1]);
      a[(m & 2) + 1][2 * j + (m & 1)] = pack2(pi[0], pi[1]);
    }
}

__device__ __forceinline__ void conv_channel(const FftConst& k, uint32_t sb, int c, int wg, int w, int lane) {
  const uint32_t cb = sb + off_ch(c), bars = sb + OFF_BAR;
  const uint32_t du = desc_lo(cb, 1024), dg = desc_lo(sb + OFF_GT, 16), dz = desc_lo(cb + U_BYTES, 16);
  float U[32], H[32];
  uint32_t a[4][4], e[4][4];
  const float dv = __uint_as_float(lds32(sb + OFF_D + 4 * c));
  wg_fence();
  WgRS<64>::set<HI_SW32>(H, k.f[0], du + 256);
  WgRS<64>::mma<HI_SW32>(H, k.f[1], du + 256 + 32);
  wg_commit();
  wg_wait<0>();
  pin<32>(H);
  twiddle_fwd(a, H, k);
  mbar_wait(bars + 8 * (B_U + (c < 3 ? c : 3)), 0);
  TSM(w == 0 && c < 3, 7 + wg);
  wg_fence();
  WgRS<64>::set<HI_SW32>(U, k.f[0], du);
  WgRS<64>::mma<HI_SW32>(U, k.f[1], du + 32);
  wg_commit();
  g_step(H, a, dg, dg + 64);
  wg_wait<1>();
  pin<32>(U);
  twiddle_fwd(e, U, k);
  wg_fence();
  g_step(U, e, dg, dg + 64);
  wg_wait<0>();
  pin<32>(U);
  pin<32>(H);
#pragma unroll
  for (int j = 0; j < 4; j++) H[4 * (j >> 1) + (j & 1)] += dv;
  float V[32];
#pragma unroll
  for (int p = 0; p < 2; p++) {
    products(a, H, U, p);
    wg_fence();
    WgRS<32>::set<HI_SW64>(V + 16 * p, a[2 * p], dg + 64);
    WgRS<32>::mma<HI_SW64>(V + 16 * p, a[2 * p + 1], dg);
    wg_commit();
  }
  const uint32_t za = cb + U_BYTES + (8 * w + (lane & 7)) * 128 + (((lane >> 3) ^ (lane & 7)) << 4);
  const uint32_t ya = cb + (lane >> 4) * 1024 + (8 * w + (lane & 7)) * 32 + ((((lane >> 3) ^ (lane >> 2)) & 1) << 4);
  wg_sync(1 + wg);
#pragma unroll
  for (int p = 0; p < 2; p++) {
    if (p == 0) wg_wait<1>();
    else wg_wait<0>();
    pin<16>(V + 16 * p);
#pragma unroll
    for (int i = 0; i < 4; i++) {
      const int j = i & 1;
      const float* x = V + 16 * p + 4 * j + (i & 2);
      e[p][i] = pack2(x[8], x[9]);
      e[2 + p][i] = pack2(x[0], x[1]);
      rot(e[p][i], e[2 + p][i], k.ta[1][j], k.tb[1][j]);
    }
    stsm4(za ^ (64 * p), e[p]);
    stsm4((za ^ (64 * p)) + 4096, e[2 + p]);
  }
  fence_async_smem();
  wg_sync(1 + wg);
  wg_fence();
  WgRS<64>::set<HI_SW128>(H, k.fi[0], dz);
#pragma unroll
  for (int ks = 1; ks < 4; ks++) WgRS<64>::mma<HI_SW128>(H, k.fi[ks], dz + 128 * ks);
  wg_commit();
  wg_wait<0>();
  pin<32>(H);
  if (lane == 0) mbar_arrive(bars + 8 * B_CVD);
  TSIF(w == 0, 88 + c);
#pragma unroll
  for (int j = 0; j < 8; j++)
    a[j >> 2][j & 3] = j < 2 ? pack2(H[4 * j], H[4 * j + 1]) : pack2(H[4 * j] + H[4 * j - 6], H[4 * j + 1] + H[4 * j - 5]);
  stsm4(ya, a[0]);
  stsm4(ya + 2048, a[1]);
  fence_async_smem();
  __syncwarp();
}

__device__ __forceinline__ void prep_slab(uint4* res, const uint2* sw, uint32_t sb, int slab, int w, int lane) {
  const int t = lane & 3, tp = (lane & 7) >> 1, pos = 8 * tp + 2 * (((lane >> 3) + tp) & 3) + (lane & 1);
  const uint32_t base = sb + OFF_KVS + slab * KVS_BYTES + pos * 128;
  uint32_t kk[2][4][4], vv[2][4];
  mbar_wait(sb + OFF_BAR + 8 * (B_KV + slab), 0);
#pragma unroll
  for (int h = 0; h < 2; h++) {
#pragma unroll
    for (int j = 0; j < 4; j++) {
      const uint32_t a = base + 128 * j;
      ldsm4t(kk[h][j], a + (((w + 4 * h) ^ ((a >> 7) & 7)) << 4));
    }
    const uint32_t a = base + KVS_V;
    ldsm4t(vv[h], a + (((w + 4 * h) ^ ((a >> 7) & 7)) << 4));
  }
#pragma unroll
  for (int h = 0; h < 2; h++) {
    uint32_t (&k)[4][4] = kk[h];
    uint32_t (&v)[4] = vv[h];
    const uint32_t w0 = __byte_perm(sw[h].x, 0, 0x1010), w1 = __byte_perm(sw[h].x, 0, 0x3232);
    const uint32_t w2 = __byte_perm(sw[h].y, 0, 0x1010), w3 = __byte_perm(sw[h].y, 0, 0x3232);
#pragma unroll
    for (int m = 0; m < 4; m++)
      v[m] = bmul(badd(badd(badd(bmul(k[0][m], w3), bmul(k[1][m], w2)), bmul(k[2][m], w1)), bmul(k[3][m], w0)), v[m]);
    uint32_t a[4];
#pragma unroll
    for (int m = 0; m < 4; m++) a[m] = (t & 1) ? v[(m + 3) & 3] : v[m];
    res[h] = (t & 2) ? make_uint4(a[2], a[3], a[0], a[1]) : make_uint4(a[0], a[1], a[2], a[3]);
  }
}

__device__ __forceinline__ void prep_gate(const Params& p, uint32_t sb, int b, int w, int lane) {
  uint2 gw[5], x[4][5];
#pragma unroll
  for (int j = 0; j < 5; j++) gw[j] = ldg64(reinterpret_cast<const uint2*>(p.gate_w) + lane + 32 * j);
#pragma unroll
  for (int i = 0; i < 4; i++)
#pragma unroll
    for (int j = 0; j < 5; j++)
      x[i][j] = ldg64(reinterpret_cast<const uint2*>(p.q) + (16 * b + 4 * w + i) * (DIM / 4) + lane + 32 * j);
  float s[4];
#pragma unroll
  for (int i = 0; i < 4; i++) {
    s[i] = 0.f;
#pragma unroll
    for (int j = 0; j < 5; j++) {
      const uint32_t m0 = bmul(x[i][j].x, gw[j].x), m1 = bmul(x[i][j].y, gw[j].y);
      s[i] += (bf_lo(m0) + bf_hi(m0)) + (bf_lo(m1) + bf_hi(m1));
    }
  }
  const bool h = lane & 16, q = lane & 8;
  const float a = (h ? s[2] : s[0]) + __shfl_xor_sync(0xffffffffu, h ? s[0] : s[2], 16);
  const float c = (h ? s[3] : s[1]) + __shfl_xor_sync(0xffffffffu, h ? s[1] : s[3], 16);
  float z = (q ? c : a) + __shfl_xor_sync(0xffffffffu, q ? a : c, 8);
#pragma unroll
  for (int o = 4; o > 0; o >>= 1) z += __shfl_xor_sync(0xffffffffu, z, o);
  z = bf_lo(pack2(z, 0.f));
  z = bf_lo(pack2(__fdividef(1.f, 1.f + __expf(-z)), 0.f));
  mbar_wait(sb + OFF_BAR + 8 * B_S3, 0);
  if ((lane & 7) == 0) asm volatile("st.shared.f32 [%0], %1;" ::"r"(sb + OFF_GATE + 64 * (b & 7) + 16 * w + (lane >> 1)), "f"(z) : "memory");
  fence_async_smem();
}

__device__ __forceinline__ uint32_t bmax(uint32_t a, uint32_t b) {
  uint32_t d;
  asm("max.bf16x2 %0, %1, %2;" : "=r"(d) : "r"(a), "r"(b));
  return d;
}
__device__ __forceinline__ void softmax_two(const float (&l)[2][2], uint32_t& p0, uint32_t& p1) {
  constexpr float kScale = 0.22360679774997896f, kLog2e = 1.4426950408889634f;
  const uint32_t r0 = pack2(l[0][0], l[1][0]), r1 = pack2(l[0][1], l[1][1]);
  const uint32_t x0 = pack2(bf_lo(r0) * kScale, bf_hi(r0) * kScale), x1 = pack2(bf_lo(r1) * kScale, bf_hi(r1) * kScale);
  uint32_t m = bmax(x0, x1);
  m = bmax(m, __shfl_xor_sync(0xffffffffu, m, 1));
  m = bmax(m, __shfl_xor_sync(0xffffffffu, m, 2));
  const float m0 = bf_lo(m) * kLog2e, m1 = bf_hi(m) * kLog2e;
  p0 = pack2(ex2(bf_lo(x0) * kLog2e - m0), ex2(bf_lo(x1) * kLog2e - m0));
  p1 = pack2(ex2(bf_hi(x0) * kLog2e - m1), ex2(bf_hi(x1) * kLog2e - m1));
}

__device__ __forceinline__ void halo_read(uint32_t (&kpv)[10], uint32_t (&vpv)[10], uint32_t (&tg)[7], const uint4* hp) {
#pragma unroll
  for (int j = 0; j < 7; j++) {
    uint32_t x0, x1, x2;
    asm volatile("ld.relaxed.gpu.global.v4.u32 {%0, %1, %2, %3}, [%4];"
                 : "=r"(x0), "=r"(x1), "=r"(x2), "=r"(tg[j]) : "l"(hp + 32 * j) : "memory");
    if (j < 4) kpv[3 * j] = x0; else vpv[3 * j - 10] = x0;
    if (j < 3) kpv[3 * j + 1] = x1; else vpv[3 * j - 9] = x1;
    if (j < 3) kpv[3 * j + 2] = x2; else if (j < 6) vpv[3 * j - 8] = x2;
  }
}

template <int ROT>
__device__ __forceinline__ void pack_qkv(const float* acc, uint32_t (&qlo)[10], uint32_t (&qhi)[10], uint32_t (&klo)[10],
                                         uint32_t (&khi)[10], uint32_t (&vlo)[10], uint32_t (&vhi)[10]) {
#pragma unroll
  for (int j = 0; j < 10; j++) {
    const int x = (j + ROT) % 10, tq = x < 8 ? x : 16 + x, tk = x < 8 ? 8 + x : 18 + x, tv = x < 8 ? 16 + x : 20 + x;
    khi[j] = pack2(acc[4 * tk + 2], acc[4 * tk + 3]);
    vhi[j] = movm(pack2(acc[4 * tv + 2], acc[4 * tv + 3]));
    qlo[j] = pack2(acc[4 * tq], acc[4 * tq + 1]);
    qhi[j] = pack2(acc[4 * tq + 2], acc[4 * tq + 3]);
    klo[j] = pack2(acc[4 * tk], acc[4 * tk + 1]);
    vlo[j] = pack2(acc[4 * tv], acc[4 * tv + 1]);
    asm volatile("" : "+r"(khi[j]), "+r"(qlo[j]), "+r"(qhi[j]), "+r"(klo[j]), "+r"(vlo[j]));
  }
}

template <int ROT> __device__ __forceinline__ void halo_send(const float* acc, uint4* ho, uint32_t tag) {
#pragma unroll
  for (int j = 0; j < 7; j++) {
    uint32_t x[3];
#pragma unroll
    for (int e = 0; e < 3; e++) {
      const int i = 3 * j + e, y = (i % 10 + ROT) % 10, tk = y < 8 ? 8 + y : 18 + y, tv = y < 8 ? 16 + y : 20 + y;
      x[e] = i < 10 ? pack2(acc[4 * tk + 2], acc[4 * tk + 3]) : i < 20 ? movm(pack2(acc[4 * tv + 2], acc[4 * tv + 3])) : 0u;
    }
    asm volatile("st.relaxed.gpu.global.v4.u32 [%0], {%1, %2, %3, %4};" ::"l"(ho + 32 * j), "r"(x[0]), "r"(x[1]), "r"(x[2]), "r"(tag) : "memory");
  }
}

__device__ __forceinline__ void attention(float* acc, uint32_t sb, int b, int par, int w, int lane, uint32_t tag) {
  const int g = lane >> 2, t = lane & 3;
  uint32_t klo[10], khi[10], vlo[10], vhi[10], qlo[10], qhi[10], kpv[10], vpv[10];
  if (w == 3 && b < NCTA - 8) {
    uint4* ho = g_halo + (b * 2 + par) * 224 + lane;
    if (tail_first(b & 7)) halo_send<8>(acc, ho, tag);
    else halo_send<0>(acc, ho, tag);
    TSIF(par == 0, 76);
    pin<120>(acc);
  }
  if (tail_first(b & 7)) pack_qkv<8>(acc, qlo, qhi, klo, khi, vlo, vhi);
  else pack_qkv<0>(acc, qlo, qhi, klo, khi, vlo, vhi);
  const uint32_t xa = sb + OFF_KVX + (par * 3) * 2560 + lane * 16;
  if (w < 3) {
    sts128(xa + w * 2560, khi[0], khi[1], khi[2], khi[3]);
    sts128(xa + w * 2560 + 512, khi[4], khi[5], khi[6], khi[7]);
    sts128(xa + w * 2560 + 1024, khi[8], khi[9], vhi[0], vhi[1]);
    sts128(xa + w * 2560 + 1536, vhi[2], vhi[3], vhi[4], vhi[5]);
    sts128(xa + w * 2560 + 2048, vhi[6], vhi[7], vhi[8], vhi[9]);
  }
  TSIF(par == 0 && w == 1, 64);
#pragma unroll
  for (int j = 0; j < 10; j++) vlo[j] = movm(vlo[j]);
  const bool far0 = 2 * t > g, far1 = 2 * t + 1 > g;
  const uint32_t mfar = (far0 ? 0x0000FFFFu : 0u) | (far1 ? 0xFFFF0000u : 0u);
  float slo[4][2], lg[2][2];
  uint32_t phi[4], plo[4], qml[4], qmh[4];
#pragma unroll
  for (int h = 0; h < 4; h++) {
    const int f = h == 0 ? 0 : h == 1 ? 3 : h == 2 ? 5 : 8, hf = h < 2 ? 2 : 7;
    const bool mine = (h & 1) ? t >= 2 : t < 2;
    qml[h] = mine ? qlo[hf] : 0u;
    qmh[h] = mine ? qhi[hf] : 0u;
    float a[4] = {0.f, 0.f, 0.f, 0.f}, c[4] = {0.f, 0.f, 0.f, 0.f};
    mma16816(a, qlo[f], qhi[f], qlo[f + 1], qhi[f + 1], klo[f], klo[f + 1]);
    mma16816(c, qlo[f], qhi[f], qlo[f + 1], qhi[f + 1], khi[f], khi[f + 1]);
    mma1688(a, qml[h], qmh[h], klo[hf]);
    mma1688(c, qml[h], qmh[h], khi[hf]);
    slo[h][0] = a[0];
    slo[h][1] = a[1];
    lg[h & 1][0] = far0 ? a[2] : c[2];
    lg[h & 1][1] = far1 ? a[3] : c[3];
    if (h & 1) softmax_two(lg, phi[h - 1], phi[h]);
  }
  TSIF(par == 0 && w == 1, 65);
  wg_sync(1 + par);
  TSIF(par == 0 && w == 1, 66);
  const bool nohist = (w == 0) && (b < 8);
  const uint4* hp = g_halo + ((b - 8) * 2 + par) * 224 + lane;
  uint32_t tg[7];
  if (w > 0) {
    const uint4 v0 = lds128(xa + (w - 1) * 2560), v1 = lds128(xa + (w - 1) * 2560 + 512), v2 = lds128(xa + (w - 1) * 2560 + 1024);
    const uint4 v3 = lds128(xa + (w - 1) * 2560 + 1536), v4 = lds128(xa + (w - 1) * 2560 + 2048);
    kpv[0] = v0.x; kpv[1] = v0.y; kpv[2] = v0.z; kpv[3] = v0.w; kpv[4] = v1.x; kpv[5] = v1.y; kpv[6] = v1.z; kpv[7] = v1.w;
    kpv[8] = v2.x; kpv[9] = v2.y; vpv[0] = v2.z; vpv[1] = v2.w; vpv[2] = v3.x; vpv[3] = v3.y; vpv[4] = v3.z; vpv[5] = v3.w;
    vpv[6] = v4.x; vpv[7] = v4.y; vpv[8] = v4.z; vpv[9] = v4.w;
  } else if (nohist) {
#pragma unroll
    for (int j = 0; j < 10; j++) kpv[j] = vpv[j] = 0u;
  } else {
    TSIF(par == 0, 77);
    halo_read(kpv, vpv, tg, hp);
  }
  if (w == 0 && !nohist) {
    int spins = 0;
    while (true) {
      bool ok = true;
#pragma unroll
      for (int j = 0; j < 7; j++) ok = ok && tg[j] == tag;
      if (__all_sync(0xffffffffu, ok) || ++spins > SPIN_LIMIT) break;
      halo_read(kpv, vpv, tg, hp);
    }
    TSIF(par == 0, 79);
  }
#pragma unroll
  for (int h = 0; h < 4; h++) {
    const int f = h == 0 ? 0 : h == 1 ? 3 : h == 2 ? 5 : 8, hf = h < 2 ? 2 : 7;
    float a[4] = {0.f, 0.f, 0.f, 0.f};
    mma16816(a, qlo[f], qhi[f], qlo[f + 1], qhi[f + 1], kpv[f], kpv[f + 1]);
    mma1688(a, qml[h], qmh[h], kpv[hf]);
    const float ninf = __int_as_float(0xff800000);
    lg[h & 1][0] = far0 ? (nohist ? ninf : a[0]) : slo[h][0];
    lg[h & 1][1] = far1 ? (nohist ? ninf : a[1]) : slo[h][1];
    if (h & 1) softmax_two(lg, plo[h - 1], plo[h]);
  }
  TSIF(par == 0 && w <= 1, 67 + w);
  uint32_t ov[20];
#pragma unroll
  for (int hp = 0; hp < 2; hp++) {
    const int hf = hp ? 7 : 2;
    float sh[4] = {0.f, 0.f, 0.f, 0.f}, i0 = 0.f, i1 = 0.f;
#pragma unroll
    for (int e = 0; e < 2; e++) {
      const int h = 2 * hp + e, f = h == 0 ? 0 : h == 1 ? 3 : h == 2 ? 5 : 8;
      const uint32_t a0 = plo[h] & mfar, a2 = plo[h] & ~mfar, a3 = phi[h] & mfar, c1 = phi[h] & ~mfar;
      float sum[4] = {0.f, 0.f, 0.f, 0.f};
      mma1688(sum, plo[h], phi[h], 0x3F803F80u);
      const float r0 = rcp(sum[0]), r1 = rcp(sum[2]);
#pragma unroll
      for (int j = f; j < f + 2; j++) {
        float o[4] = {0.f, 0.f, 0.f, 0.f};
        mma16816(o, a0, 0u, a2, a3, vpv[j], vlo[j]);
        mma1688(o, 0u, c1, vhi[j]);
        ov[2 * j] = pack2(o[0] * r0, o[1] * r0);
        ov[2 * j + 1] = pack2(o[2] * r1, o[3] * r1);
      }
      const bool mine = e ? g >= 4 : g < 4;
      mma16816(sh, a0, 0u, a2, a3, mine ? vpv[hf] : 0u, mine ? vlo[hf] : 0u);
      mma1688(sh, 0u, c1, mine ? vhi[hf] : 0u);
      if (e == 0 || t >= 2) {
        i0 = r0;
        i1 = r1;
      }
    }
    ov[2 * hf] = pack2(sh[0] * i0, sh[1] * i0);
    ov[2 * hf + 1] = pack2(sh[2] * i1, sh[3] * i1);
  }
  TS(32 + 4 * par + w);
  mbar_wait(sb + OFF_BAR + 8 * B_P1, 0);
  const uint32_t oa = sb + OFF_OA + (lane >> 4) * 2048 + (32 * w + 2 * (lane & 15) + par) * 16;
#pragma unroll
  for (int j = 0; j < 5; j++) stsm4(oa + 4096 * j, ov + 4 * j);
  TSIF(par == 0 && w == 0, 120);
  fence_async_smem();
  TSIF(par == 0 && w == 0, 121);
  __syncwarp();
  if (lane == 0) mbar_arrive(sb + OFF_BAR + 8 * B_ATTN);
  TSM(w == 0 || w == 2, 122 + par + (w == 2 ? 3 : 0));
}

struct Maps {
  CUtensorMap x, wm, wt, k, v, y, wo, qm, qt, om, ot, yl, ol;
};

__device__ __forceinline__ void load_stage(uint32_t sb, int kb, int b, const Maps& m) {
  const uint32_t st = sb + (kb & 3) * STAGE_BYTES, bar = sb + OFF_BAR + 8 * (B_FULL1 + (kb & 3));
  const int r = b >> 3, hg = b & 7, slab = kb - KV_KB;
  const bool kv = slab >= 0 && slab < 5;
  const uint32_t kbar = sb + OFF_BAR + 8 * (B_KV + slab), dst = sb + OFF_KVS + slab * KVS_BYTES;
  mbar_expect_tx(bar, STAGE_BYTES);
  if (kv) mbar_expect_tx(kbar, KVS_BYTES);
  tma_3d(st, &m.x, 64 * kb, 64 * r, 0, bar);
  tma_3d(st + ST_W, &m.wm, 80 * hg + (tail_first(hg) ? 16 : 0), 64 * kb, 0, bar);
  tma_3d(st + ST_WT, &m.wt, 80 * hg + (tail_first(hg) ? 0 : 64), 64 * kb, 0, bar);
  if (kv) tma_3d(dst, &m.k, 0, 32 * (b >> 1) - 3, 2 * slab + (b & 1), kbar);
  if (kv) tma_3d(dst + KVS_V, &m.v, 0, 32 * (b >> 1), 2 * slab + (b & 1), kbar);
}

__global__ void __launch_bounds__(NTHR, 1) fused_kernel(const __grid_constant__ Maps m, const Params p) {
  extern __shared__ __align__(1024) uint8_t smem[];
  const uint32_t sb = (uint32_t)__cvta_generic_to_shared(smem);
  const uint32_t bars = sb + OFF_BAR;
  const int tid = threadIdx.x, lane = tid & 31;
  int b = blockIdx.x;
  b = (((b & 63) >> 3) * 2 + (b & 1)) * 8 + (((b < 64 ? 0x6521 : 0x7430) >> (4 * ((b >> 1) & 3))) & 7);
  const int r = b >> 3, hg = b & 7;

  if (tid == T_ISSUE) {
    TSM(true, 0);
    mbar_init(bars + 8 * B_F0, 1);
    fence_async_smem();
    mbar_expect_tx(bars + 8 * B_F0, ST_WT);
    tma_3d(sb, &m.x, 0, 64 * r, 0, bars + 8 * B_F0);
    tma_3d(sb + ST_W, &m.wm, 80 * hg + (tail_first(hg) ? 16 : 0), 0, 0, bars + 8 * B_F0);
#pragma unroll
    for (int i = 0; i < 4; i++) mbar_init(bars + 8 * (B_FULL1 + i), 1);
    fence_async_smem();
    mbar_expect_tx(bars + 8 * B_FULL1, STAGE_BYTES - ST_WT);
    tma_3d(sb + ST_WT, &m.wt, 80 * hg + (tail_first(hg) ? 0 : 64), 0, 0, bars + 8 * B_FULL1);
    load_stage(sb, 1, b, m);
  } else if (tid == T_INIT) {
#pragma unroll
    for (int i = 0; i < B_F0; i++) mbar_init(bars + 8 * i, i < B_GATE ? 8 : i < B_CVD ? 4 : i == B_CVD ? 20 : 1);
    fence_async_smem();
  }
  const int warp = __shfl_sync(0xffffffffu, tid >> 5, 0), wg = warp >> 2, w = warp & 3;
  __syncthreads();

  if (wg == 3) {
    asm volatile("setmaxnreg.dec.sync.aligned.u32 56;");
    if (w == 0) {
      if (lane == 0) {
#pragma unroll 1
        for (int kb = 2; kb < 10; kb++) {
          if (kb >= 4) mbar_wait(bars + 8 * (kb == 7 ? B_E3 : B_EMPTY1 + (kb & 3)), (kb >> 3) & 1);
          TSIF(kb >= 4, 44 + kb);
          load_stage(sb, kb, b, m);
          TSIF(kb == 3, 60);
          if (kb == 9) mbar_arrive(bars + 8 * B_LAST);
        }
        mbar_wait(bars + 8 * B_WOP, 0);
        mbar_wait(bars + 8 * B_EPOCH, 0);
        flag_wait(g_cnt + C_W + 32 * hg, (lds32(sb + OFF_EPOCH) + 1) * 16);
        TS(30);
#pragma unroll 1
        for (int j = 0; j < 8; j++) {
          if (j >= 6) mbar_wait(bars + 8 * (B_EMPTY2 + j - 6), 0);
          if (j == 4) mbar_wait(bars + 8 * B_ORB, 0);
          TSIF(j >= 6, 100 + j);
          mbar_expect_tx(bars + 8 * (B_FULL2 + j), j == 0 ? WO_BYTES : j == 5 ? O_BYTES + WO_BYTES + 512 : O_BYTES + WO_BYTES);
          bulk_load(sb + off_w(j), g_WO + (hg * 8 + step_src(hg, j)) * 800, WO_BYTES, bars + 8 * (B_FULL2 + j));
        }
        mbar_wait(bars + 8 * (B_EMPTY2 + 3), 0);
        mbar_expect_tx(bars + 8 * B_QF, O_BYTES);
        tma_2d(sb + OFF_QS, &m.qm, 80 * hg, 128 * r, bars + 8 * B_QF);
        tma_2d(sb + OFF_QT, &m.qt, 80 * hg + 64, 128 * r, bars + 8 * B_QF);
      }
    } else if (w == 1) {
      unsigned epoch = 0;
      if (lane == 0) {
        epoch = atomicAdd(g_cnt + C_LAUNCH, 1u) / NCTA;
        asm volatile("st.shared.u32 [%0], %1;" ::"r"(sb + OFF_EPOCH), "r"(epoch) : "memory");
        mbar_arrive(bars + 8 * B_EPOCH);
        mbar_wait(bars + 8 * B_KVD, 0);
        mbar_expect_tx(bars + 8 * B_HB, 5 * 4096);
#pragma unroll 1
        for (int c = 0; c < 5; c++) {
          if (c == 3) mbar_wait(bars + 8 * B_S3, 0);
          bulk_load(sb + off_ch(c) + U_BYTES, p.ssm_k + (5 * b + c) * SEQ, 4096, bars + 8 * B_HB);
        }
#pragma unroll
        for (int c = 0; c < 4; c++) mbar_expect_tx(bars + 8 * (B_U + c), c < 3 ? U_BYTES : 2 * U_BYTES);
        const uint4* usrc = g_U + 5 * b * U_PITCH;
        mbar_wait(bars + 8 * B_USIG, 0);
        flag_wait(g_cnt + C_PREP + 32 * (b & 15), (epoch + 1) * NCTA);
        TS(23);
#pragma unroll
        for (int c = 0; c < 5; c++) {
          if (c == 3) mbar_wait(bars + 8 * (B_U + 2), 0);
          bulk_load(sb + off_ch(c), usrc + c * U_PITCH, U_BYTES, bars + 8 * (B_U + (c < 3 ? c : 3)));
          TSIF(c == 0 || c == 4, 116 + (c >> 2));
        }
      }
      epoch = __shfl_sync(0xffffffffu, epoch, 0);
      if (lane < 8) {
        const int src = (b & ~7) | step_src(hg, lane);
        mbar_wait(bars + 8 * B_ATTN, 0);
        TS(20);
        bool seen = false;
#pragma unroll 1
        for (int spins = 0; spins < SPIN_LIMIT; spins++) {
          const bool now = !seen && (int)(flag_read(g_cnt + C_O + 32 * src) - (epoch + 1)) >= 0;
          if (now && lane >= 1 && lane < 4) bulk_load(sb + off_o(lane), g_O + src * 1280, O_BYTES, bars + 8 * (B_FULL2 + lane));
          seen = seen || now;
          if (__all_sync(0xff, seen)) break;
        }
        TS(21);
        if (lane == 5) bulk_load(sb + OFF_GATE, g_gate + 128 * r, 512, bars + 8 * (B_FULL2 + 5));
#pragma unroll 1
        for (int j = 4; j < 8; j++) {
          if (lane == j) {
            mbar_wait(bars + 8 * (j < 6 ? B_C34 : B_EMPTY2 + j - 6), 0);
            bulk_load(sb + off_o(j), g_O + src * 1280, O_BYTES, bars + 8 * (B_FULL2 + j));
          }
          __syncwarp(0xff);
        }
        TS(22);
      }
    } else if (w == 2) {
      mbar_wait(bars + 8 * B_PREP, 0);
      flag_signal(g_cnt + C_PREP, 16, lane);
      TS(25);
      if (lane == 0) {
        mbar_arrive(bars + 8 * B_USIG);
        mbar_expect_tx(bars + 8 * B_ORB, O_BYTES / 4 + 64);
        mbar_wait(bars + 8 * B_GATE, 0);
        publish(g_gate + 16 * b, sb + OFF_GATE + 64 * hg, 64);
        bulk_load(sb + OFF_GATE + 64 * hg, g_gate + 16 * b, 64, bars + 8 * B_ORB);
        mbar_wait(bars + 8 * B_ATTN, 0);
        publish(g_O + b * 1280, sb + OFF_OA, O_BYTES);
        tma_2d(sb + OFF_KVX + 10240, &m.ol, 48, b * 160, bars + 8 * B_ORB);
        TS(74);
        mbar_wait(bars + 8 * B_ORB, 0);
        flag_bump(g_cnt + C_O + 32 * b);
        TS(26);
      }
    } else {
      if (lane == 0) {
        uint4* dst = g_WO + (hg * 8 + (r >> 1)) * 800 + (r & 1) * 80;
        mbar_wait(bars + 8 * B_S3, 0);
        asm volatile("cp.async.bulk.prefetch.L2.global [%0], 6400;" ::"l"(p.wo + b * 3200) : "memory");
        mbar_wait(bars + 8 * B_P1, 0);
        mbar_wait(bars + 8 * WB_TRIG, 0);
        mbar_expect_tx(bars + 8 * B_WST, WO_BYTES / 2);
        tma_3d(sb + OFF_WA, &m.wo, 0, 40 * r, 5 * hg, bars + 8 * B_WST);
        mbar_wait(bars + 8 * B_WST, 0);
#pragma unroll 1
        for (int n = 0; n < 5; n++) bulk_store(dst + 160 * n, sb + OFF_WA + 1280 * n, 1280);
        bulk_wait_read();
        mbar_expect_tx(bars + 8 * B_WST, WO_BYTES / 2);
#pragma unroll 1
        for (int n = 0; n < 5; n++) bulk_load(sb + OFF_WA + 1280 * n, dst + 160 * n, 1280, bars + 8 * B_WST);
        mbar_wait(bars + 8 * B_WST, 1);
        flag_bump(g_cnt + C_W + 32 * hg);
        mbar_arrive(bars + 8 * B_WOP);
        TS(71);
        mbar_expect_tx(bars + 8 * B_C34, 3 * (U_BYTES / 4));
        mbar_expect_tx(bars + 8 * B_YRB, 2 * (U_BYTES / 4));
#pragma unroll 1
        for (int c = 0; c < 5; c++) {
          mbar_wait(bars + 8 * (B_YST + c), 0);
          publish(g_U + (5 * b + c) * U_PITCH, sb + off_ch(c), U_BYTES);
          tma_2d(sb + off_ch(c), &m.yl, 48, (5 * b + c) * (U_PITCH / 8), bars + 8 * (c < 3 ? B_C34 : B_YRB));
        }
        TS(75);
        mbar_wait(bars + 8 * B_C34, 0);
        mbar_wait(bars + 8 * B_YRB, 0);
        flag_bump(g_cnt + C_Y + 32 * (b >> 4));
        TS(27);
        mbar_expect_tx(bars + 8 * B_YFULL, 20480);
        flag_wait(g_cnt + C_Y + 32 * hg, (lds32(sb + OFF_EPOCH) + 1) * 16);
        TS(24);
        tma_2d(sb + OFF_YT, &m.y, 128 * r, 80 * hg, bars + 8 * B_YFULL);
        tma_2d(sb + OFF_YT + 10240, &m.y, 128 * r + 64, 80 * hg, bars + 8 * B_YFULL);
      }
    }
  } else {
    asm volatile("setmaxnreg.inc.sync.aligned.u32 152;");
    if (wg < 2) {
      float acc[120];
#pragma unroll
      for (int i = 0; i < 120; i++) acc[i] = 0.f;
      const uint32_t da = desc_lo(sb + wg * 8192, 16), db = desc_lo(sb + ST_W, 8192), dc = desc_lo(sb + ST_WT, 2048);
      mbar_wait(bars + 8 * B_F0, 0);
      TSIF(w == 0 && wg == 0, 1);
      wg_fence();
#pragma unroll
      for (int k = 0; k < 4; k++) WgSST<192>::mma<HI_SW128, HI_SW128>(acc, da + 2 * k, db + 128 * k, 1);
      wg_commit();
      mbar_wait(bars + 8 * B_FULL1, 0);
      wg_fence();
#pragma unroll
      for (int k = 0; k < 4; k++) WgSST<48>::mma<HI_SW128, HI_SW32>(acc + 96, da + 2 * k, dc + 32 * k, 1);
      wg_commit();
#pragma unroll 1
      for (int kb = 1; kb < 10; kb++) {
        mbar_wait(bars + 8 * (B_FULL1 + (kb & 3)), (kb >> 2) & 1);
        const uint32_t so = (kb & 3) * (STAGE_BYTES >> 4);
        wg_fence();
#pragma unroll
        for (int k = 0; k < 4; k++) {
          WgSST<192>::mma<HI_SW128, HI_SW128>(acc, da + so + 2 * k, db + so + 128 * k, 1);
          WgSST<48>::mma<HI_SW128, HI_SW32>(acc + 96, da + so + 2 * k, dc + so + 32 * k, 1);
        }
        wg_commit();
        wg_wait<1>();
        if (lane == 0) mbar_arrive(bars + 8 * (kb == 4 ? B_E3 : B_EMPTY1 + ((kb - 1) & 3)));
      }
      mbar_wait(bars + 8 * B_EPOCH, 0);
      const uint32_t tag = lds32(sb + OFF_EPOCH) + 1;
      mbar_wait(bars + 8 * B_S3, 0);
      wg_wait<0>();
      pin<120>(acc);
      if (lane == 0) mbar_arrive(bars + 8 * B_P1);
      TSM(w == 0, 3 + wg);
      attention(acc, sb, b, wg, w, lane, tag);
    } else {
      const int tw = tid & 127, chl = 64 * (b & 1) + 8 * w + (lane >> 2);
      uint4* up = g_U + chl * U_PITCH + ((4 * (b >> 1) + (lane & 3)) ^ ((b >> 2) & 1));
      uint2 sw[10];
      uint32_t dv = 0;
      if (lane < 5) dv = __ldg(reinterpret_cast<const unsigned short*>(p.ssm_D) + 5 * b + lane);
#pragma unroll
      for (int i = 0; i < 10; i++) sw[i] = ldg64(reinterpret_cast<const uint2*>(p.shift_k) + chl + 128 * (i >> 1) + 32 * (i & 1));
      uint32_t tab[12];
      uint32_t tt[2];
      fft_tables(tab, tw);
      fft_twiddles(tt, tw);
      uint4 res[10];
#pragma unroll
      for (int i = 0; i < 10; i++) res[i] = make_uint4(0, 0, 0, 0);
#pragma unroll 1
      for (int slab = 0; slab < 5; slab++) {
#pragma unroll
        for (int i = 0; i < 8; i++) res[i] = res[i + 2];
        prep_slab(res + 8, sw, sb, slab, w, lane);
        TSIF(w == 0, 99 + 4 * slab);
#pragma unroll
        for (int i = 0; i < 8; i++) sw[i] = sw[i + 2];
      }
      TSIF(w == 0, 28);
      __syncwarp();
      if (lane == 0) mbar_arrive(bars + 8 * B_KVD + ((res[8].x ^ res[9].x) & p.zero));
      mbar_wait(bars + 8 * B_KVD, 0);
      fft_tables_store(tab, sb, tw);
      mbar_wait(bars + 8 * B_LAST, 0);
#pragma unroll
      for (int i = 0; i < 10; i++) up[(128 * (i >> 1) + 32 * (i & 1)) * U_PITCH] = res[i];
      __syncwarp();
      if (lane == 0) mbar_arrive(bars + 8 * B_PREP);
      TSIF(w == 0, 5);
      mbar_wait(bars + 8 * B_LAST, 0);
      prep_gate(p, sb, b, w, lane);
      __syncwarp();
      if (lane == 0) mbar_arrive(bars + 8 * B_GATE);
      TSIF(w == 0, 72);
      mbar_wait(bars + 8 * B_HB, 0);
      TSIF(w == 0, 2);
      const uint32_t ha = sb + U_BYTES + ((tw >> 3) * 16 + 8 + (tw & 7)) * 16;
      uint4 hv[5];
#pragma unroll
      for (int c = 0; c < 5; c++) hv[c] = lds128(ha + off_ch(c));
      __syncwarp();
#pragma unroll
      for (int c = 0; c < 5; c++) sts128((ha ^ 16) + off_ch(c), hv[c].x, hv[c].y, hv[c].z, hv[c].w);
      asm volatile("st.shared.v2.u32 [%0], {%1, %2};" ::"r"(sb + OFF_TT + 8 * tw), "r"(tt[0]), "r"(tt[1]) : "memory");
      if (tw < 5) asm volatile("st.shared.f32 [%0], %1;" ::"r"(sb + OFF_D + 4 * tw), "f"(bf_lo(dv) * 0.125f) : "memory");
      fence_async_smem();
      __syncwarp();
      if (lane == 0) mbar_arrive(bars + 8 * B_HA);
      TSIF(w == 0, 6);
    }

    FftConst fc;
    TSM(w == 0 && wg == 0, 104);
    mbar_wait(bars + 8 * B_HA, 0);
    fft_matrices(fc, sb, w, lane);
    TSM(w == 0 && wg == 0, 105);
    TSM(w == 0 && wg == 2, 124);
#pragma unroll 1
    for (uint32_t tasks = wg == 0 ? TASK0 : wg == 1 ? TASK1 : TASK2; tasks; tasks >>= 4) {
      const int c = (tasks & 7) - 1;
      conv_channel(fc, sb, c, wg, w, lane);
      if (lane == 0) mbar_arrive(bars + 8 * (B_YST + c));
      TSM(w == 0, 10 + c);
    }

    if (wg != 1) {
      const int wg = warp >> 3;
      const int g = lane >> 2;
      float acc[40];
#pragma unroll
      for (int i = 0; i < 40; i++) acc[i] = 0.f;
      const uint32_t da = desc_lo(sb + wg * 1024, 2048), db = desc_lo(sb, 2560);
      mbar_wait(bars + 8 * B_ORB, 0);
      mbar_wait(bars + 8 * B_FULL2, 0);
      TSM(w == 0, 15 + wg);
#pragma unroll 1
      for (int j = 0; j < 8; j++) {
        if (j == 1 - wg) mbar_wait(bars + 8 * B_CVD, 0);
        mbar_wait(bars + 8 * (B_FULL2 + j), 0);
        TSM(w == 0 && wg == 0, 44 + (j < 4 ? j : j + 6));
        const uint32_t oa = da + (off_o(j) >> 4), ob = db + (off_w(j) >> 4);
        wg_fence();
#pragma unroll
        for (int k = 0; k < 5; k++) WgSST<80>::mma<HI_NONE, HI_SW32>(acc, oa + 256 * k, ob + 32 * k, 1);
        wg_commit();
        wg_wait<1>();
        if (j >= 1 && j <= 4 && lane == 0) mbar_arrive(bars + 8 * (B_EMPTY2 + j - 1));
      }
      TSIF(w == 0 && wg == 0, 113);
      const int tr = 64 * wg + 16 * w + (lane & 15);
      const uint32_t fm = sb + OFF_QS + tr * 128, fx = (lane >> 4) ^ (tr & 7);
      const uint32_t ft = sb + OFF_QT + tr * 32 + (((lane >> 4) ^ (tr >> 2)) & 1) * 16;
      const float g0 = __uint_as_float(lds32(sb + OFF_GATE + (64 * wg + 16 * w + g) * 4));
      const float g1 = __uint_as_float(lds32(sb + OFF_GATE + (64 * wg + 16 * w + 8 + g) * 4));
      const uint32_t ga = pack2(g0, g0), gb = pack2(g1, g1);
      const uint32_t na = pack2(1.f - g0, 1.f - g0), nb = pack2(1.f - g1, 1.f - g1);

      uint32_t qf[20];
      mbar_wait(bars + 8 * B_QF, 0);
      TSM(w == 0 && wg == 0, 99);
#pragma unroll
      for (int j = 0; j < 5; j++) ldsm4(qf + 4 * j, j < 4 ? fm + ((fx ^ (2 * j)) << 4) : ft);
#pragma unroll
      for (int i = 0; i < 20; i++) {
        qf[i] = bmul((i & 1) ? gb : ga, qf[i]);
        asm volatile("" : "+r"(qf[i]));
      }

      wg_wait<0>();
      pin<40>(acc);
      TSM(w == 0, 17 + wg);
      uint32_t pb[20];
#pragma unroll
      for (int j = 0; j < 10; j++) {
        pb[2 * j] = bmul(na, pack2(acc[4 * j], acc[4 * j + 1]));
        pb[2 * j + 1] = bmul(nb, pack2(acc[4 * j + 2], acc[4 * j + 3]));
        asm volatile("" : "+r"(pb[2 * j]), "+r"(pb[2 * j + 1]));
      }
      const uint32_t ya = sb + OFF_YT + wg * 10240 + ((lane >> 4) * 8 + (lane & 7)) * 128 +
                          (((2 * w + (((lane >> 3) & 1) ^ wg)) ^ (lane & 7)) << 4);
      mbar_wait(bars + 8 * B_YFULL, 0);
      TSM(w == 0 && wg == 0, 19);
#pragma unroll
      for (int j = 0; j < 5; j++) {
        uint32_t y[4];
        ldsm4t(y, ya + 2048 * j);
#pragma unroll
        for (int i = 0; i < 4; i++)
          qf[4 * j + i] = bfma(qf[4 * j + i], y[i], pb[4 * j + i]);
      }
#pragma unroll
      for (int j = 0; j < 5; j++) stsm4(j < 4 ? fm + ((fx ^ (2 * j)) << 4) : ft, qf + 4 * j);
      fence_async_smem();
      __syncwarp();
      if (lane == 0) {
        const int row = 64 * wg + 16 * w;
        asm volatile("cp.async.bulk.tensor.2d.global.shared::cta.bulk_group [%0, {%2, %3}], [%1];"
                     ::"l"(&m.om), "r"(sb + OFF_QS + row * 128), "r"(80 * hg), "r"(128 * r + row) : "memory");
        asm volatile("cp.async.bulk.tensor.2d.global.shared::cta.bulk_group [%0, {%2, %3}], [%1];"
                     ::"l"(&m.ot), "r"(sb + OFF_QT + row * 32), "r"(80 * hg + 64), "r"(128 * r + row) : "memory");
        asm volatile("cp.async.bulk.commit_group;\ncp.async.bulk.wait_group.read 0;" ::: "memory");
      }
      TSM(w == 0 || w == 3, 40 + 2 * wg + (w & 1));
    }
  }
}

typedef CUresult (*EncodeFn)(CUtensorMap*, CUtensorMapDataType, cuuint32_t, void*, const cuuint64_t*, const cuuint64_t*,
                             const cuuint32_t*, const cuuint32_t*, CUtensorMapInterleave, CUtensorMapSwizzle,
                             CUtensorMapL2promotion, CUtensorMapFloatOOBfill);

void encode(EncodeFn fn, CUtensorMap* tm, const void* base, int rank, const cuuint64_t* dims, const cuuint64_t* strides,
            const cuuint32_t* box, CUtensorMapSwizzle swz) {
  const cuuint32_t ones[3] = {1, 1, 1};
  fn(tm, CU_TENSOR_MAP_DATA_TYPE_BFLOAT16, rank, const_cast<void*>(base), dims, strides, box, ones,
     CU_TENSOR_MAP_INTERLEAVE_NONE, swz, CU_TENSOR_MAP_L2_PROMOTION_L2_128B, CU_TENSOR_MAP_FLOAT_OOB_FILL_NONE);
}

}

extern "C" void kernel_launch(void* const* d_in, const int* in_sizes, int n_in, void* d_out, int out_size) {
  (void)in_sizes; (void)n_in; (void)out_size;
  Params p;
  p.q = (const __nv_bfloat16*)d_in[0];
  p.k = (const __nv_bfloat16*)d_in[1];
  p.v = (const __nv_bfloat16*)d_in[2];
  p.shift_k = (const __nv_bfloat16*)d_in[3];
  p.ssm_k = (const __nv_bfloat16*)d_in[4];
  p.ssm_D = (const __nv_bfloat16*)d_in[5];
  p.wqkv = (const __nv_bfloat16*)d_in[7];
  p.wo = (const __nv_bfloat16*)d_in[8];
  p.gate_w = (const __nv_bfloat16*)d_in[9];
  p.out = (__nv_bfloat16*)d_out;
  p.zero = 0;

  static EncodeFn fn = nullptr;
  static void *yaddr = nullptr, *oaddr = nullptr;
  if (!fn) {
    cudaDriverEntryPointQueryResult qr;
    void* f = nullptr;
    cudaGetDriverEntryPoint("cuTensorMapEncodeTiled", &f, cudaEnableDefault, &qr);
    fn = (EncodeFn)f;
    cudaGetSymbolAddress(&yaddr, g_U);
    cudaGetSymbolAddress(&oaddr, g_O);
    cudaFuncSetAttribute(fused_kernel, cudaFuncAttributeMaxDynamicSharedMemorySize, SMEM_BYTES);
  }
  Maps m;
  {
    const cuuint64_t dims[3] = {640, 1024, 2}, st[2] = {2560, 1280};
    const cuuint32_t box[3] = {64, 64, 2};
    encode(fn, &m.x, p.q, 3, dims, st, box, CU_TENSOR_MAP_SWIZZLE_128B);
  }
  {
    const cuuint64_t dims[3] = {640, 640, 3}, st[2] = {3840, 1280};
    const cuuint32_t box[3] = {64, 64, 3}, boxt[3] = {16, 64, 3};
    encode(fn, &m.wm, p.wqkv, 3, dims, st, box, CU_TENSOR_MAP_SWIZZLE_128B);
    encode(fn, &m.wt, p.wqkv, 3, dims, st, boxt, CU_TENSOR_MAP_SWIZZLE_32B);
  }
  {
    const cuuint64_t dims[3] = {64, 2048, 10}, st[2] = {1280, 128};
    const cuuint32_t boxk[3] = {64, 35, 1}, boxv[3] = {64, 32, 1};
    encode(fn, &m.k, p.k, 3, dims, st, boxk, CU_TENSOR_MAP_SWIZZLE_128B);
    encode(fn, &m.v, p.v, 3, dims, st, boxv, CU_TENSOR_MAP_SWIZZLE_128B);
  }
  {
    const cuuint64_t dims[3] = {16, 640, 40}, st[2] = {1280, 32};
    const cuuint32_t box[3] = {16, 40, 5};
    encode(fn, &m.wo, p.wo, 3, dims, st, box, CU_TENSOR_MAP_SWIZZLE_32B);
  }
  {
    const cuuint64_t dims[2] = {2048, 640}, st[1] = {U_PITCH * 16};
    const cuuint32_t box[2] = {64, 80};
    encode(fn, &m.y, yaddr, 2, dims, st, box, CU_TENSOR_MAP_SWIZZLE_128B);
    const cuuint64_t dl[2] = {64, DIM * U_PITCH / 8}, dol[2] = {64, NCTA * 160}, sl[1] = {128};
    const cuuint32_t bl[2] = {16, 32}, bol[2] = {16, 160};
    encode(fn, &m.yl, yaddr, 2, dl, sl, bl, CU_TENSOR_MAP_SWIZZLE_NONE);
    encode(fn, &m.ol, oaddr, 2, dol, sl, bol, CU_TENSOR_MAP_SWIZZLE_NONE);
  }
  {
    const cuuint64_t dims[2] = {640, 2048}, st[1] = {1280};
    const cuuint32_t bqm[2] = {64, 128}, bqt[2] = {16, 128}, bom[2] = {64, 16}, bot[2] = {16, 16};
    encode(fn, &m.qm, p.q, 2, dims, st, bqm, CU_TENSOR_MAP_SWIZZLE_128B);
    encode(fn, &m.qt, p.q, 2, dims, st, bqt, CU_TENSOR_MAP_SWIZZLE_32B);
    encode(fn, &m.om, p.out, 2, dims, st, bom, CU_TENSOR_MAP_SWIZZLE_128B);
    encode(fn, &m.ot, p.out, 2, dims, st, bot, CU_TENSOR_MAP_SWIZZLE_32B);
  }
  fused_kernel<<<NCTA, NTHR, SMEM_BYTES>>>(m, p);
}
```

```cpp
#include <cuda.h>
#include <cuda_bf16.h>
#include <cuda_runtime.h>
#include <stdint.h>

namespace {

constexpr int SEQ = 2048, DIM = 640, NCTA = 128, NTHR = 512;

#define KV_KB 2
#define DEV_EXIT 0
#define FENCE_LO 0
#define FENCE_HI 0
#define WB_TRIG B_USIG
#define T_ISSUE 288
#define SRC_ORD 1
#define T_INIT 448
#define TASK0 0x3
#define TASK1 0x52
#define TASK2 0x41

constexpr uint32_t STAGE_BYTES = 47104, ST_W = 16384, ST_WT = 40960;
constexpr uint32_t O_BYTES = 20480, WO_BYTES = 12800;
constexpr uint32_t OFF_OA = 0;
constexpr uint32_t OFF_QS = 3 * O_BYTES, OFF_QT = OFF_QS + 16384;
constexpr uint32_t OFF_WC = 81920;
constexpr uint32_t OFF_WA = 94720;
constexpr uint32_t OFF_GATE = 145920;
constexpr uint32_t OFF_TT = 146432;
constexpr uint32_t OFF_KVX = 148480;
constexpr uint32_t OFF_CH3 = 163840;
constexpr uint32_t CH_BYTES = 12288, U_BYTES = 4096;
constexpr uint32_t OFF_FT = 225280, OFF_GT = 229376;
constexpr uint32_t OFF_CH0 = 188416;
constexpr uint32_t OFF_KVS = OFF_CH0, KVS_V = 4480, KVS_BYTES = 8576;
constexpr uint32_t OFF_YT = 163840;
constexpr uint32_t OFF_BAR = 231936;
constexpr uint32_t SMEM_BYTES = OFF_BAR + 512;

enum : uint32_t {
  B_EMPTY1 = 0, B_S3 = 3, B_E3 = 4, B_EMPTY2 = 5, B_ATTN = 9, B_P1 = 10,
  B_GATE = 11, B_HA = 12, B_KVD = 13, B_PREP = 14, B_YST = 15,
  B_CVD = 20,
  B_FULL2 = 21, B_U = 29, B_KV = 33, B_HB = 38, B_C34 = 39, B_YRB = 40, B_YFULL = 41, B_EPOCH = 42, B_LAST = 43,
  B_WOP = 44, B_USIG = 45, B_WST = 46, B_QF = 47, B_ORB = 48,
  B_F0 = 49, B_FULL1 = 50
};
constexpr uint32_t OFF_EPOCH = OFF_BAR + 8 * 58, OFF_D = OFF_BAR + 8 * 60;
__device__ __forceinline__ uint32_t off_o(int j) { return j < 4 ? OFF_OA + j * O_BYTES : j < 6 ? OFF_CH0 + (j - 4) * O_BYTES : OFF_OA + (j - 6) * O_BYTES; }
__device__ __forceinline__ uint32_t off_w(int j) { return j < 4 ? OFF_WA + j * WO_BYTES : j == 4 ? OFF_KVX : j == 5 ? OFF_WC : OFF_WA + (j - 6) * WO_BYTES; }
__device__ __forceinline__ int step_src(int hg, int j) {
  if (SRC_ORD) {
    const int pos = (0x37621540 >> (4 * hg)) & 7;
    return j == 0 ? hg : (0x65217430 >> (4 * (j <= pos ? j - 1 : j))) & 7;
  }
  return j == 0 ? hg : j <= hg ? j - 1 : j;
}
__device__ __forceinline__ bool tail_first(int hg) { return (hg & 3) == 3; }
__device__ __forceinline__ uint32_t off_ch(int c) { return (c < 3 ? OFF_CH0 : OFF_CH3 - 3 * CH_BYTES) + c * CH_BYTES; }

#define U_PITCH 264
__device__ __align__(1024) uint4 g_U[DIM * U_PITCH];
__device__ __align__(128) uint4 g_O[NCTA * 1280];
__device__ uint4 g_WO[64 * 800];
__device__ uint4 g_halo[NCTA * 2 * 7 * 32];
__device__ __align__(128) float g_gate[SEQ];
__device__ unsigned g_cnt[32 * (1 + 2 * 16 + 8 + NCTA)];
constexpr int C_LAUNCH = 0, C_PREP = 32, C_Y = 32 * 17, C_W = 32 * 33, C_O = 32 * 41;

#define TSM(cond, slot) do { } while (0)
#define TSIF(cond, slot) do { if (__LINE__ >= FENCE_LO && __LINE__ < FENCE_HI) sched_fence(); } while (0)
__device__ __forceinline__ void sched_fence() {
  asm volatile("{\n.reg .pred p;\n.reg .u32 c;\nmov.u32 c, %%clock;\nsetp.eq.u32 p, c, 0;\n@p st.shared.u32 [%0], c;\n}"
               ::"r"(1024 + OFF_EPOCH + 4) : "memory");
}
#define TS(slot) TSIF(true, slot)

struct Params {
  const __nv_bfloat16 *q, *k, *v, *shift_k, *ssm_k, *ssm_D, *wqkv, *wo, *gate_w;
  __nv_bfloat16* out;
  uint32_t zero;
};

constexpr int SPIN_LIMIT = 1 << 17;

__device__ __forceinline__ void mbar_init(uint32_t bar, uint32_t count) {
  asm volatile("mbarrier.init.shared::cta.b64 [%0], %1;" ::"r"(bar), "r"(count) : "memory");
}
__device__ __forceinline__ void mbar_expect_tx(uint32_t bar, uint32_t bytes) {
  asm volatile("mbarrier.arrive.expect_tx.shared::cta.b64 _, [%0], %1;" ::"r"(bar), "r"(bytes) : "memory");
}
__device__ __forceinline__ void mbar_arrive(uint32_t bar) {
  asm volatile("mbarrier.arrive.shared::cta.b64 _, [%0];" ::"r"(bar) : "memory");
}
__device__ __forceinline__ void mbar_wait(uint32_t bar, uint32_t parity) {
  uint32_t ok;
  int spins = 0;
  do {
      asm volatile("{\n.reg .pred p;\nmbarrier.try_wait.parity.shared::cta.b64 p, [%1], %2;\nselp.b32 %0, 1, 0, p;\n}"
                   : "=r"(ok) : "r"(bar), "r"(parity) : "memory");
    if (++spins > SPIN_LIMIT) break;
  } while (!ok);
}
__device__ __forceinline__ unsigned flag_read(const unsigned* p) {
  unsigned v;
  asm volatile("ld.relaxed.gpu.global.u32 %0, [%1];" : "=r"(v) : "l"(p) : "memory");
  return v;
}
__device__ __forceinline__ void flag_poll(const unsigned* p, unsigned target) {
  unsigned v;
  int spins = 0;
  do {
    asm volatile("ld.relaxed.gpu.global.u32 %0, [%1];" : "=r"(v) : "l"(p) : "memory");
    if (++spins > SPIN_LIMIT) break;
  } while ((int)(v - target) < 0);
}
__device__ __forceinline__ void flag_wait(const unsigned* p, unsigned target) {
  flag_poll(p, target);
}
__device__ __forceinline__ void flag_signal(unsigned* p, int n, int lane) {
  if (lane == 0) asm volatile("fence.release.gpu;" ::: "memory");
  __syncwarp();
  if (lane < n) asm volatile("red.relaxed.gpu.global.add.u32 [%0], 1;" ::"l"(p + 32 * lane) : "memory");
}
__device__ __forceinline__ void flag_bump(unsigned* p) {
  asm volatile("red.relaxed.gpu.global.add.u32 [%0], 1;" ::"l"(p) : "memory");
}
__device__ __forceinline__ void fence_async_smem() { asm volatile("fence.proxy.async.shared::cta;" ::: "memory"); }
__device__ __forceinline__ void wg_sync(int id) { asm volatile("bar.sync %0, 128;" ::"r"(id) : "memory"); }

__device__ __forceinline__ void tma_2d(uint32_t dst, const CUtensorMap* tm, int c0, int c1, uint32_t bar) {
  asm volatile("cp.async.bulk.tensor.2d.shared::cluster.global.mbarrier::complete_tx::bytes [%0], [%1, {%3, %4}], [%2];"
               ::"r"(dst), "l"(tm), "r"(bar), "r"(c0), "r"(c1) : "memory");
}
__device__ __forceinline__ void tma_3d(uint32_t dst, const CUtensorMap* tm, int c0, int c1, int c2, uint32_t bar) {
  asm volatile("cp.async.bulk.tensor.3d.shared::cluster.global.mbarrier::complete_tx::bytes [%0], [%1, {%3, %4, %5}], [%2];"
               ::"r"(dst), "l"(tm), "r"(bar), "r"(c0), "r"(c1), "r"(c2) : "memory");
}
__device__ __forceinline__ void bulk_load(uint32_t dst, const void* src, uint32_t bytes, uint32_t bar) {
  asm volatile("cp.async.bulk.shared::cluster.global.mbarrier::complete_tx::bytes [%0], [%1], %2, [%3];"
               ::"r"(dst), "l"(src), "r"(bytes), "r"(bar) : "memory");
}
__device__ __forceinline__ void bulk_store(void* dst, uint32_t src, uint32_t bytes) {
  asm volatile("cp.async.bulk.global.shared::cta.bulk_group [%0], [%1], %2;" ::"l"(dst), "r"(src), "r"(bytes) : "memory");
}
__device__ __forceinline__ void bulk_wait_read() {
  asm volatile("cp.async.bulk.commit_group;\ncp.async.bulk.wait_group.read 0;" ::: "memory");
}

__device__ __forceinline__ void publish(void* dst, uint32_t src, uint32_t bytes) {
  bulk_store(dst, src, bytes);
  bulk_wait_read();
}

__device__ __forceinline__ void wg_fence() { asm volatile("wgmma.fence.sync.aligned;" ::: "memory"); }
__device__ __forceinline__ void wg_commit() { asm volatile("wgmma.commit_group.sync.aligned;" ::: "memory"); }
template <int N> __device__ __forceinline__ void wg_wait() { asm volatile("wgmma.wait_group.sync.aligned %0;" ::"n"(N) : "memory"); }
__device__ __forceinline__ uint32_t desc_lo(uint32_t addr, uint32_t lbo) { return ((addr & 0x3FFFF) >> 4) | ((lbo >> 4) << 16); }
constexpr uint32_t desc_hi(uint32_t sbo, uint32_t swz) { return (sbo >> 4) | (swz << 30); }
constexpr uint32_t HI_SW128 = desc_hi(1024, 1), HI_SW64 = desc_hi(512, 2), HI_SW32 = desc_hi(256, 3), HI_NONE = desc_hi(128, 0);
template <int N> __device__ __forceinline__ void pin(float* d) {
#pragma unroll
  for (int i = 0; i < N; i++) asm volatile("" : "+f"(d[i])::"memory");
}

__device__ __forceinline__ uint32_t lds32(uint32_t a) {
  uint32_t v;
  asm volatile("ld.volatile.shared.u32 %0, [%1];" : "=r"(v) : "r"(a) : "memory");
  return v;
}
__device__ __forceinline__ uint2 ldg64(const void* a) {
  uint2 v;
  asm volatile("ld.global.nc.v2.u32 {%0, %1}, [%2];" : "=r"(v.x), "=r"(v.y) : "l"(a) : "memory");
  return v;
}
__device__ __forceinline__ void ldsm4(uint32_t* r, uint32_t a) {
  asm volatile("ldmatrix.sync.aligned.m8n8.x4.shared.b16 {%0, %1, %2, %3}, [%4];"
               : "=r"(r[0]), "=r"(r[1]), "=r"(r[2]), "=r"(r[3]) : "r"(a) : "memory");
}
__device__ __forceinline__ void ldsm4t(uint32_t* r, uint32_t a) {
  asm volatile("ldmatrix.sync.aligned.m8n8.x4.trans.shared.b16 {%0, %1, %2, %3}, [%4];"
               : "=r"(r[0]), "=r"(r[1]), "=r"(r[2]), "=r"(r[3]) : "r"(a) : "memory");
}
__device__ __forceinline__ uint2 lds64(uint32_t a) {
  uint2 v;
  asm volatile("ld.shared.v2.u32 {%0, %1}, [%2];" : "=r"(v.x), "=r"(v.y) : "r"(a) : "memory");
  return v;
}
__device__ __forceinline__ uint4 lds128(uint32_t a) {
  uint4 v;
  asm volatile("ld.shared.v4.u32 {%0, %1, %2, %3}, [%4];" : "=r"(v.x), "=r"(v.y), "=r"(v.z), "=r"(v.w) : "r"(a) : "memory");
  return v;
}
__device__ __forceinline__ void sts128(uint32_t a, uint32_t x, uint32_t y, uint32_t z, uint32_t w) {
  asm volatile("st.shared.v4.u32 [%0], {%1, %2, %3, %4};" ::"r"(a), "r"(x), "r"(y), "r"(z), "r"(w) : "memory");
}
__device__ __forceinline__ void stsm4(uint32_t a, const uint32_t* r) {
  asm volatile("stmatrix.sync.aligned.m8n8.x4.shared.b16 [%0], {%1, %2, %3, %4};" ::"r"(a), "r"(r[0]), "r"(r[1]), "r"(r[2]), "r"(r[3]) : "memory");
}
__device__ __forceinline__ uint32_t pack2(float lo, float hi) {
  uint32_t r;
  asm("cvt.rn.bf16x2.f32 %0, %1, %2;" : "=r"(r) : "f"(hi), "f"(lo));
  return r;
}
__device__ __forceinline__ uint32_t movm(uint32_t a) {
  uint32_t d;
  asm volatile("movmatrix.sync.aligned.m8n8.trans.b16 %0, %1;" : "=r"(d) : "r"(a));
  return d;
}
__device__ __forceinline__ uint32_t bmul(uint32_t a, uint32_t b) {
  uint32_t d;
  asm("mul.rn.bf16x2 %0, %1, %2;" : "=r"(d) : "r"(a), "r"(b));
  return d;
}
__device__ __forceinline__ uint32_t badd(uint32_t a, uint32_t b) {
  uint32_t d;
  asm("add.rn.bf16x2 %0, %1, %2;" : "=r"(d) : "r"(a), "r"(b));
  return d;
}
__device__ __forceinline__ uint32_t bfma(uint32_t a, uint32_t b, uint32_t c) {
  uint32_t d;
  asm("fma.rn.bf16x2 %0, %1, %2, %3;" : "=r"(d) : "r"(a), "r"(b), "r"(c));
  return d;
}
__device__ __forceinline__ float bf_lo(uint32_t x) { return __uint_as_float(x << 16); }
__device__ __forceinline__ float bf_hi(uint32_t x) { return __uint_as_float(x & 0xFFFF0000u); }
__device__ __forceinline__ float ex2(float x) {
  float y;
  asm("ex2.approx.ftz.f32 %0, %1;" : "=f"(y) : "f"(x));
  return y;
}
__device__ __forceinline__ float rcp(float x) {
  float y;
  asm("rcp.approx.ftz.f32 %0, %1;" : "=f"(y) : "f"(x));
  return y;
}
__device__ __forceinline__ void mma16816(float* d, uint32_t a0, uint32_t a1, uint32_t a2, uint32_t a3, uint32_t b0, uint32_t b1) {
  asm volatile("mma.sync.aligned.m16n8k16.row.col.f32.bf16.bf16.f32 {%0, %1, %2, %3}, {%4, %5, %6, %7}, {%8, %9}, {%0, %1, %2, %3};"
               : "+f"(d[0]), "+f"(d[1]), "+f"(d[2]), "+f"(d[3])
               : "r"(a0), "r"(a1), "r"(a2), "r"(a3), "r"(b0), "r"(b1));
}
__device__ __forceinline__ void mma1688(float* d, uint32_t a0, uint32_t a1, uint32_t b0) {
  asm volatile("mma.sync.aligned.m16n8k8.row.col.f32.bf16.bf16.f32 {%0, %1, %2, %3}, {%4, %5}, {%6}, {%0, %1, %2, %3};"
               : "+f"(d[0]), "+f"(d[1]), "+f"(d[2]), "+f"(d[3])
               : "r"(a0), "r"(a1), "r"(b0));
}

template <int N> struct WgRS;
template <int N> struct WgSST;
template <> struct WgRS<32> {
  template <uint32_t HB>
  static __device__ __forceinline__ void mma(float* d, const uint32_t* a, uint32_t db) {
    asm volatile("{\n.reg .pred p;\n.reg .b64 db;\nsetp.ne.b32 p, %22, 0;\n"
      "mov.b64 db, {%20, %21};\n"
      "wgmma.mma_async.sync.aligned.m64n32k16.f32.bf16.bf16 {"
      "%0, %1, %2, %3, %4, %5, %6, %7, %8, %9, %10, %11, %12, %13, %14, %15"
      "}, {%16, %17, %18, %19}, db, p, 1, 1, 1;\n}\n"
      : "+f"(d[0]), "+f"(d[1]), "+f"(d[2]), "+f"(d[3]), "+f"(d[4]), "+f"(d[5]), "+f"(d[6]), "+f"(d[7]),
        "+f"(d[8]), "+f"(d[9]), "+f"(d[10]), "+f"(d[11]), "+f"(d[12]), "+f"(d[13]), "+f"(d[14]), "+f"(d[15])
      : "r"(a[0]), "r"(a[1]), "r"(a[2]), "r"(a[3]), "r"(db), "n"(HB), "n"(1));
  }
  template <uint32_t HB>
  static __device__ __forceinline__ void set(float* d, const uint32_t* a, uint32_t db) {
    asm volatile("{\n.reg .pred p;\n.reg .b64 db;\nsetp.ne.b32 p, %22, 0;\n"
      "mov.b64 db, {%20, %21};\n"
      "wgmma.mma_async.sync.aligned.m64n32k16.f32.bf16.bf16 {"
      "%0, %1, %2, %3, %4, %5, %6, %7, %8, %9, %10, %11, %12, %13, %14, %15"
      "}, {%16, %17, %18, %19}, db, p, 1, 1, 1;\n}\n"
      : "=f"(d[0]), "=f"(d[1]), "=f"(d[2]), "=f"(d[3]), "=f"(d[4]), "=f"(d[5]), "=f"(d[6]), "=f"(d[7]),
        "=f"(d[8]), "=f"(d[9]), "=f"(d[10]), "=f"(d[11]), "=f"(d[12]), "=f"(d[13]), "=f"(d[14]), "=f"(d[15])
      : "r"(a[0]), "r"(a[1]), "r"(a[2]), "r"(a[3]), "r"(db), "n"(HB), "n"(0));
  }
};
template <> struct WgRS<64> {
  template <uint32_t HB>
  static __device__ __forceinline__ void mma(float* d, const uint32_t* a, uint32_t db) {
    asm volatile("{\n.reg .pred p;\n.reg .b64 db;\nsetp.ne.b32 p, %38, 0;\n"
      "mov.b64 db, {%36, %37};\n"
      "wgmma.mma_async.sync.aligned.m64n64k16.f32.bf16.bf16 {"
      "%0, %1, %2, %3, %4, %5, %6, %7, %8, %9, %10, %11, %12, %13, %14, %15, "
      "%16, %17, %18, %19, %20, %21, %22, %23, %24, %25, %26, %27, %28, %29, %30, %31"
      "}, {%32, %33, %34, %35}, db, p, 1, 1, 1;\n}\n"
      : "+f"(d[0]), "+f"(d[1]), "+f"(d[2]), "+f"(d[3]), "+f"(d[4]), "+f"(d[5]), "+f"(d[6]), "+f"(d[7]),
        "+f"(d[8]), "+f"(d[9]), "+f"(d[10]), "+f"(d[11]), "+f"(d[12]), "+f"(d[13]), "+f"(d[14]), "+f"(d[15]),
        "+f"(d[16]), "+f"(d[17]), "+f"(d[18]), "+f"(d[19]), "+f"(d[20]), "+f"(d[21]), "+f"(d[22]), "+f"(d[23]),
        "+f"(d[24]), "+f"(d[25]), "+f"(d[26]), "+f"(d[27]), "+f"(d[28]), "+f"(d[29]), "+f"(d[30]), "+f"(d[31])
      : "r"(a[0]), "r"(a[1]), "r"(a[2]), "r"(a[3]), "r"(db), "n"(HB), "n"(1));
  }
  template <uint32_t HB>
  static __device__ __forceinline__ void set(float* d, const uint32_t* a, uint32_t db) {
    asm volatile("{\n.reg .pred p;\n.reg .b64 db;\nsetp.ne.b32 p, %38, 0;\n"
      "mov.b64 db, {%36, %37};\n"
      "wgmma.mma_async.sync.aligned.m64n64k16.f32.bf16.bf16 {"
      "%0, %1, %2, %3, %4, %5, %6, %7, %8, %9, %10, %11, %12, %13, %14, %15, "
      "%16, %17, %18, %19, %20, %21, %22, %23, %24, %25, %26, %27, %28, %29, %30, %31"
      "}, {%32, %33, %34, %35}, db, p, 1, 1, 1;\n}\n"
      : "=f"(d[0]), "=f"(d[1]), "=f"(d[2]), "=f"(d[3]), "=f"(d[4]), "=f"(d[5]), "=f"(d[6]), "=f"(d[7]),
        "=f"(d[8]), "=f"(d[9]), "=f"(d[10]), "=f"(d[11]), "=f"(d[12]), "=f"(d[13]), "=f"(d[14]), "=f"(d[15]),
        "=f"(d[16]), "=f"(d[17]), "=f"(d[18]), "=f"(d[19]), "=f"(d[20]), "=f"(d[21]), "=f"(d[22]), "=f"(d[23]),
        "=f"(d[24]), "=f"(d[25]), "=f"(d[26]), "=f"(d[27]), "=f"(d[28]), "=f"(d[29]), "=f"(d[30]), "=f"(d[31])
      : "r"(a[0]), "r"(a[1]), "r"(a[2]), "r"(a[3]), "r"(db), "n"(HB), "n"(0));
  }
};
template <> struct WgSST<48> {
  template <uint32_t HA, uint32_t HB>
  static __device__ __forceinline__ void mma(float* d, uint32_t da, uint32_t db, int sc) {
    asm volatile("{\n.reg .pred p;\n.reg .b64 da, db;\nsetp.ne.b32 p, %28, 0;\n"
      "mov.b64 da, {%24, %25};\nmov.b64 db, {%26, %27};\n"
      "wgmma.mma_async.sync.aligned.m64n48k16.f32.bf16.bf16 {"
      "%0, %1, %2, %3, %4, %5, %6, %7, %8, %9, %10, %11, %12, %13, %14, %15, "
      "%16, %17, %18, %19, %20, %21, %22, %23"
      "}, da, db, p, 1, 1, 0, 1;\n}\n"
      : "+f"(d[0]), "+f"(d[1]), "+f"(d[2]), "+f"(d[3]), "+f"(d[4]), "+f"(d[5]), "+f"(d[6]), "+f"(d[7]),
        "+f"(d[8]), "+f"(d[9]), "+f"(d[10]), "+f"(d[11]), "+f"(d[12]), "+f"(d[13]), "+f"(d[14]), "+f"(d[15]),
        "+f"(d[16]), "+f"(d[17]), "+f"(d[18]), "+f"(d[19]), "+f"(d[20]), "+f"(d[21]), "+f"(d[22]), "+f"(d[23])
      : "r"(da), "n"(HA), "r"(db), "n"(HB), "r"(sc));
  }
};
template <> struct WgSST<80> {
  template <uint32_t HA, uint32_t HB>
  static __device__ __forceinline__ void mma(float* d, uint32_t da, uint32_t db, int sc) {
    asm volatile("{\n.reg .pred p;\n.reg .b64 da, db;\nsetp.ne.b32 p, %44, 0;\n"
      "mov.b64 da, {%40, %41};\nmov.b64 db, {%42, %43};\n"
      "wgmma.mma_async.sync.aligned.m64n80k16.f32.bf16.bf16 {"
      "%0, %1, %2, %3, %4, %5, %6, %7, %8, %9, %10, %11, %12, %13, %14, %15, "
      "%16, %17, %18, %19, %20, %21, %22, %23, %24, %25, %26, %27, %28, %29, %30, %31, "
      "%32, %33, %34, %35, %36, %37, %38, %39"
      "}, da, db, p, 1, 1, 0, 1;\n}\n"
      : "+f"(d[0]), "+f"(d[1]), "+f"(d[2]), "+f"(d[3]), "+f"(d[4]), "+f"(d[5]), "+f"(d[6]), "+f"(d[7]),
        "+f"(d[8]), "+f"(d[9]), "+f"(d[10]), "+f"(d[11]), "+f"(d[12]), "+f"(d[13]), "+f"(d[14]), "+f"(d[15]),
        "+f"(d[16]), "+f"(d[17]), "+f"(d[18]), "+f"(d[19]), "+f"(d[20]), "+f"(d[21]), "+f"(d[22]), "+f"(d[23]),
        "+f"(d[24]), "+f"(d[25]), "+f"(d[26]), "+f"(d[27]), "+f"(d[28]), "+f"(d[29]), "+f"(d[30]), "+f"(d[31]),
        "+f"(d[32]), "+f"(d[33]), "+f"(d[34]), "+f"(d[35]), "+f"(d[36]), "+f"(d[37]), "+f"(d[38]), "+f"(d[39])
      : "r"(da), "n"(HA), "r"(db), "n"(HB), "r"(sc));
  }
};
template <> struct WgSST<192> {
  template <uint32_t HA, uint32_t HB>
  static __device__ __forceinline__ void mma(float* d, uint32_t da, uint32_t db, int sc) {
    asm volatile("{\n.reg .pred p;\n.reg .b64 da, db;\nsetp.ne.b32 p, %100, 0;\n"
      "mov.b64 da, {%96, %97};\nmov.b64 db, {%98, %99};\n"
      "wgmma.mma_async.sync.aligned.m64n192k16.f32.bf16.bf16 {"
      "%0, %1, %2, %3, %4, %5, %6, %7, %8, %9, %10, %11, %12, %13, %14, %15, "
      "%16, %17, %18, %19, %20, %21, %22, %23, %24, %25, %26, %27, %28, %29, %30, %31, "
      "%32, %33, %34, %35, %36, %37, %38, %39, %40, %41, %42, %43, %44, %45, %46, %47, "
      "%48, %49, %50, %51, %52, %53, %54, %55, %56, %57, %58, %59, %60, %61, %62, %63, "
      "%64, %65, %66, %67, %68, %69, %70, %71, %72, %73, %74, %75, %76, %77, %78, %79, "
      "%80, %81, %82, %83, %84, %85, %86, %87, %88, %89, %90, %91, %92, %93, %94, %95"
      "}, da, db, p, 1, 1, 0, 1;\n}\n"
      : "+f"(d[0]), "+f"(d[1]), "+f"(d[2]), "+f"(d[3]), "+f"(d[4]), "+f"(d[5]), "+f"(d[6]), "+f"(d[7]),
        "+f"(d[8]), "+f"(d[9]), "+f"(d[10]), "+f"(d[11]), "+f"(d[12]), "+f"(d[13]), "+f"(d[14]), "+f"(d[15]),
        "+f"(d[16]), "+f"(d[17]), "+f"(d[18]), "+f"(d[19]), "+f"(d[20]), "+f"(d[21]), "+f"(d[22]), "+f"(d[23]),
        "+f"(d[24]), "+f"(d[25]), "+f"(d[26]), "+f"(d[27]), "+f"(d[28]), "+f"(d[29]), "+f"(d[30]), "+f"(d[31]),
        "+f"(d[32]), "+f"(d[33]), "+f"(d[34]), "+f"(d[35]), "+f"(d[36]), "+f"(d[37]), "+f"(d[38]), "+f"(d[39]),
        "+f"(d[40]), "+f"(d[41]), "+f"(d[42]), "+f"(d[43]), "+f"(d[44]), "+f"(d[45]), "+f"(d[46]), "+f"(d[47]),
        "+f"(d[48]), "+f"(d[49]), "+f"(d[50]), "+f"(d[51]), "+f"(d[52]), "+f"(d[53]), "+f"(d[54]), "+f"(d[55]),
        "+f"(d[56]), "+f"(d[57]), "+f"(d[58]), "+f"(d[59]), "+f"(d[60]), "+f"(d[61]), "+f"(d[62]), "+f"(d[63]),
        "+f"(d[64]), "+f"(d[65]), "+f"(d[66]), "+f"(d[67]), "+f"(d[68]), "+f"(d[69]), "+f"(d[70]), "+f"(d[71]),
        "+f"(d[72]), "+f"(d[73]), "+f"(d[74]), "+f"(d[75]), "+f"(d[76]), "+f"(d[77]), "+f"(d[78]), "+f"(d[79]),
        "+f"(d[80]), "+f"(d[81]), "+f"(d[82]), "+f"(d[83]), "+f"(d[84]), "+f"(d[85]), "+f"(d[86]), "+f"(d[87]),
        "+f"(d[88]), "+f"(d[89]), "+f"(d[90]), "+f"(d[91]), "+f"(d[92]), "+f"(d[93]), "+f"(d[94]), "+f"(d[95])
      : "r"(da), "n"(HA), "r"(db), "n"(HB), "r"(sc));
  }
};

struct FftConst {
  uint32_t f[2][4], fi[4][4];
  uint32_t ta[2][2], tb[2][2];
};
__device__ __forceinline__ void cis(int m, float scale, float& c, float& s) {
  const float a = (float)m * (-6.283185307179586f * scale);
  c = __cosf(a);
  s = __sinf(a);
}
__device__ __forceinline__ void fft_tables(uint32_t (&v)[12], int tw) {
  const int row = tw >> 2, ch = tw & 3;
#pragma unroll
  for (int i = 0; i < 4; i++) {
    float c[2], s[2], x[2];
#pragma unroll
    for (int e = 0; e < 2; e++) {
      cis((((32 * (8 * ch + 2 * i + e) + 15) * (4 * row - 63) + 2048) & 4095) - 2048, 1.f / 4096, c[e], s[e]);
      float gc, gs;
      cis((((row & 15) * (8 * (ch & 1) + 2 * i + e) + 8) & 15) - 8, 1.f / 16, gc, gs);
      x[e] = (row >> 4) == (ch >> 1) ? gc : (ch >> 1) ? gs : -gs;
    }
    v[i] = pack2(c[0] * 0.125f, c[1] * 0.125f);
    v[4 + i] = pack2(s[0] * 0.125f, s[1] * 0.125f);
    v[8 + i] = pack2(x[0], x[1]);
  }
#pragma unroll
  for (int i = 0; i < 12; i++) asm volatile("" : "+r"(v[i]));
}
__device__ __forceinline__ void fft_tables_store(const uint32_t (&v)[12], uint32_t sb, int tw) {
  const int row = tw >> 2;
  const uint32_t x = ((tw ^ (row >> 1)) & 3) << 4, a = sb + OFF_FT + (16 * (row >> 3) + (row & 7)) * 64 + x;
  sts128(a, v[0], v[1], v[2], v[3]);
  sts128(a + 512, v[4], v[5], v[6], v[7]);
  sts128(sb + OFF_GT + row * 64 + x, v[8], v[9], v[10], v[11]);
}
__device__ __forceinline__ void fft_twiddles(uint32_t (&v)[2], int tw) {
  float a[2], s[2];
#pragma unroll
  for (int i = 0; i < 2; i++) {
    float c;
    cis((2 * (2 * (tw & 3) + i) - 15) * (4 * (tw >> 2) - 63), 1.f / 4096, c, s[i]);
    a[i] = __fdividef(-s[i], 1.f + c);
  }
  v[0] = pack2(a[0], a[1]);
  v[1] = pack2(s[0], s[1]);
  asm volatile("" : "+r"(v[0]), "+r"(v[1]));
}
__device__ __forceinline__ void fft_matrices(FftConst& k, uint32_t sb, int w, int lane) {
  const uint32_t x = (lane >> 1) & 3;
  const uint2 t0 = lds64(sb + OFF_TT + 256 * w + 8 * lane), t1 = lds64(sb + OFF_TT + 256 * w + 8 * (lane ^ 3));
  k.ta[0][0] = t0.x;
  k.tb[0][0] = t0.y;
  k.ta[1][1] = __byte_perm(t1.x, 0, 0x1032);
  k.tb[1][1] = __byte_perm(t1.y, 0, 0x1032);
#pragma unroll
  for (int j = 0; j < 2; j++) {
    k.ta[1 - j][j] = k.ta[j][j] ^ 0x80008000u;
    k.tb[1 - j][j] = k.tb[j][j] ^ 0x80008000u;
    asm volatile("" : "+r"(k.ta[0][j]), "+r"(k.tb[0][j]), "+r"(k.ta[1][j]), "+r"(k.tb[1][j]));
  }
#pragma unroll
  for (int i = 0; i < 2; i++) {
    ldsm4(k.f[i], sb + OFF_FT + (16 * w + (lane & 15)) * 64 + (((2 * i + (lane >> 4)) ^ x) << 4));
    ldsm4t(k.fi[i], sb + OFF_FT + (32 * i + lane) * 64 + ((w ^ x) << 4));
#pragma unroll
    for (int j = 0; j < 4; j++) {
      k.fi[2 + i][j] = (j & 1) ? k.fi[i][j - 1] ^ 0x80008000u : k.fi[i][j + 1];
      asm volatile("" : "+r"(k.fi[2 + i][j]));
    }
  }
}
__device__ __forceinline__ void rot(uint32_t& x, uint32_t& y, uint32_t a, uint32_t b) {
  x = bfma(a, y, x);
  y = bfma(b, x, y);
  x = bfma(a, y, x);
}
__device__ __forceinline__ void twiddle_fwd(uint32_t (&a)[4][4], float* d, const FftConst& k) {
#pragma unroll
  for (int q = 0; q < 4; q++)
#pragma unroll
    for (int j = 0; j < 2; j++) {
      const float* x = d + 8 * q + 4 * j;
      uint32_t re = pack2(x[0], x[1]), im = pack2(x[2], x[3]);
      rot(re, im, k.ta[0][j], k.tb[0][j]);
      a[q & 2][2 * j + (q & 1)] = re;
      a[(q & 2) + 1][2 * j + (q & 1)] = im;
    }
}
__device__ __forceinline__ void g_step(float* d, const uint32_t (&a)[4][4], uint32_t dre, uint32_t dim) {
  WgRS<32>::set<HI_SW64>(d, a[0], dre);
  WgRS<32>::set<HI_SW64>(d + 16, a[2], dre);
  WgRS<32>::mma<HI_SW64>(d, a[1], dim);
  WgRS<32>::mma<HI_SW64>(d + 16, a[3], dim);
  wg_commit();
}

__device__ __forceinline__ void products(uint32_t (&a)[4][4], const float* H, const float* U, int p) {
#pragma unroll
  for (int j = 0; j < 2; j++)
#pragma unroll
    for (int m = 2 * p; m < 2 * p + 2; m++) {
      float pr[2], pi[2];
#pragma unroll
      for (int x = 0; x < 2; x++)
#pragma unroll
        for (int q = 0; q <= m; q++) {
          const int ih = 16 * (q >> 1) + 2 * (q & 1) + 4 * j + x, iu = 16 * ((m - q) >> 1) + 2 * ((m - q) & 1) + 4 * j + x;
          pr[x] = q ? fmaf(H[ih], U[iu], pr[x]) : H[ih] * U[iu];
          pi[x] = q ? fmaf(H[ih], U[iu + 8], pi[x]) : H[ih] * U[iu + 8];
          pr[x] = fmaf(-H[ih + 8], U[iu + 8], pr[x]);
          pi[x] = fmaf(H[ih + 8], U[iu], pi[x]);
        }
      a[m & 2][2 * j + (m & 1)] = pack2(pr[0], pr[1]);
      a[(m & 2) + 1][2 * j + (m & 1)] = pack2(pi[0], pi[1]);
    }
}

__device__ __forceinline__ void conv_channel(const FftConst& k, uint32_t sb, int c, int wg, int w, int lane) {
  const uint32_t cb = sb + off_ch(c), bars = sb + OFF_BAR;
  const uint32_t du = desc_lo(cb, 1024), dg = desc_lo(sb + OFF_GT, 16), dz = desc_lo(cb + U_BYTES, 16);
  float U[32], H[32];
  uint32_t a[4][4], e[4][4];
  const float dv = __uint_as_float(lds32(sb + OFF_D + 4 * c));
  wg_fence();
  WgRS<64>::set<HI_SW32>(H, k.f[0], du + 256);
  WgRS<64>::mma<HI_SW32>(H, k.f[1], du + 256 + 32);
  wg_commit();
  wg_wait<0>();
  pin<32>(H);
  twiddle_fwd(a, H, k);
  mbar_wait(bars + 8 * (B_U + (c < 3 ? c : 3)), 0);
  TSM(w == 0 && c < 3, 7 + wg);
  wg_fence();
  WgRS<64>::set<HI_SW32>(U, k.f[0], du);
  WgRS<64>::mma<HI_SW32>(U, k.f[1], du + 32);
  wg_commit();
  g_step(H, a, dg, dg + 64);
  wg_wait<1>();
  pin<32>(U);
  twiddle_fwd(e, U, k);
  wg_fence();
  g_step(U, e, dg, dg + 64);
  wg_wait<0>();
  pin<32>(U);
  pin<32>(H);
#pragma unroll
  for (int j = 0; j < 4; j++) H[4 * (j >> 1) + (j & 1)] += dv;
  float V[32];
#pragma unroll
  for (int p = 0; p < 2; p++) {
    products(a, H, U, p);
    wg_fence();
    WgRS<32>::set<HI_SW64>(V + 16 * p, a[2 * p], dg + 64);
    WgRS<32>::mma<HI_SW64>(V + 16 * p, a[2 * p + 1], dg);
    wg_commit();
  }
  const uint32_t za = cb + U_BYTES + (8 * w + (lane & 7)) * 128 + (((lane >> 3) ^ (lane & 7)) << 4);
  const uint32_t ya = cb + (lane >> 4) * 1024 + (8 * w + (lane & 7)) * 32 + ((((lane >> 3) ^ (lane >> 2)) & 1) << 4);
  wg_sync(1 + wg);
#pragma unroll
  for (int p = 0; p < 2; p++) {
    if (p == 0) wg_wait<1>();
    else wg_wait<0>();
    pin<16>(V + 16 * p);
#pragma unroll
    for (int i = 0; i < 4; i++) {
      const int j = i & 1;
      const float* x = V + 16 * p + 4 * j + (i & 2);
      e[p][i] = pack2(x[8], x[9]);
      e[2 + p][i] = pack2(x[0], x[1]);
      rot(e[p][i], e[2 + p][i], k.ta[1][j], k.tb[1][j]);
    }
    stsm4(za ^ (64 * p), e[p]);
    stsm4((za ^ (64 * p)) + 4096, e[2 + p]);
  }
  fence_async_smem();
  wg_sync(1 + wg);
  wg_fence();
  WgRS<64>::set<HI_SW128>(H, k.fi[0], dz);
#pragma unroll
  for (int ks = 1; ks < 4; ks++) WgRS<64>::mma<HI_SW128>(H, k.fi[ks], dz + 128 * ks);
  wg_commit();
  wg_wait<0>();
  pin<32>(H);
  if (lane == 0) mbar_arrive(bars + 8 * B_CVD);
  TSIF(w == 0, 88 + c);
#pragma unroll
  for (int j = 0; j < 8; j++)
    a[j >> 2][j & 3] = j < 2 ? pack2(H[4 * j], H[4 * j + 1]) : pack2(H[4 * j] + H[4 * j - 6], H[4 * j + 1] + H[4 * j - 5]);
  stsm4(ya, a[0]);
  stsm4(ya + 2048, a[1]);
  fence_async_smem();
  __syncwarp();
}

__device__ __forceinline__ void prep_slab(uint4* res, const uint2* sw, uint32_t sb, int slab, int w, int lane) {
  const int t = lane & 3, tp = (lane & 7) >> 1, pos = 8 * tp + 2 * (((lane >> 3) + tp) & 3) + (lane & 1);
  const uint32_t base = sb + OFF_KVS + slab * KVS_BYTES + pos * 128;
  uint32_t kk[2][4][4], vv[2][4];
  mbar_wait(sb + OFF_BAR + 8 * (B_KV + slab), 0);
#pragma unroll
  for (int h = 0; h < 2; h++) {
#pragma unroll
    for (int j = 0; j < 4; j++) {
      const uint32_t a = base + 128 * j;
      ldsm4t(kk[h][j], a + (((w + 4 * h) ^ ((a >> 7) & 7)) << 4));
    }
    const uint32_t a = base + KVS_V;
    ldsm4t(vv[h], a + (((w + 4 * h) ^ ((a >> 7) & 7)) << 4));
  }
#pragma unroll
  for (int h = 0; h < 2; h++) {
    uint32_t (&k)[4][4] = kk[h];
    uint32_t (&v)[4] = vv[h];
    const uint32_t w0 = __byte_perm(sw[h].x, 0, 0x1010), w1 = __byte_perm(sw[h].x, 0, 0x3232);
    const uint32_t w2 = __byte_perm(sw[h].y, 0, 0x1010), w3 = __byte_perm(sw[h].y, 0, 0x3232);
#pragma unroll
    for (int m = 0; m < 4; m++)
      v[m] = bmul(badd(badd(badd(bmul(k[0][m], w3), bmul(k[1][m], w2)), bmul(k[2][m], w1)), bmul(k[3][m], w0)), v[m]);
    uint32_t a[4];
#pragma unroll
    for (int m = 0; m < 4; m++) a[m] = (t & 1) ? v[(m + 3) & 3] : v[m];
    res[h] = (t & 2) ? make_uint4(a[2], a[3], a[0], a[1]) : make_uint4(a[0], a[1], a[2], a[3]);
  }
}

__device__ __forceinline__ void prep_gate(const Params& p, uint32_t sb, int b, int w, int lane) {
  uint2 gw[5], x[4][5];
#pragma unroll
  for (int j = 0; j < 5; j++) gw[j] = ldg64(reinterpret_cast<const uint2*>(p.gate_w) + lane + 32 * j);
#pragma unroll
  for (int i = 0; i < 4; i++)
#pragma unroll
    for (int j = 0; j < 5; j++)
      x[i][j] = ldg64(reinterpret_cast<const uint2*>(p.q) + (16 * b + 4 * w + i) * (DIM / 4) + lane + 32 * j);
  float s[4];
#pragma unroll
  for (int i = 0; i < 4; i++) {
    s[i] = 0.f;
#pragma unroll
    for (int j = 0; j < 5; j++) {
      const uint32_t m0 = bmul(x[i][j].x, gw[j].x), m1 = bmul(x[i][j].y, gw[j].y);
      s[i] += (bf_lo(m0) + bf_hi(m0)) + (bf_lo(m1) + bf_hi(m1));
    }
  }
  const bool h = lane & 16, q = lane & 8;
  const float a = (h ? s[2] : s[0]) + __shfl_xor_sync(0xffffffffu, h ? s[0] : s[2], 16);
  const float c = (h ? s[3] : s[1]) + __shfl_xor_sync(0xffffffffu, h ? s[1] : s[3], 16);
  float z = (q ? c : a) + __shfl_xor_sync(0xffffffffu, q ? a : c, 8);
#pragma unroll
  for (int o = 4; o > 0; o >>= 1) z += __shfl_xor_sync(0xffffffffu, z, o);
  z = bf_lo(pack2(z, 0.f));
  z = bf_lo(pack2(__fdividef(1.f, 1.f + __expf(-z)), 0.f));
  mbar_wait(sb + OFF_BAR + 8 * B_S3, 0);
  if ((lane & 7) == 0) asm volatile("st.shared.f32 [%0], %1;" ::"r"(sb + OFF_GATE + 64 * (b & 7) + 16 * w + (lane >> 1)), "f"(z) : "memory");
  fence_async_smem();
}

__device__ __forceinline__ uint32_t bmax(uint32_t a, uint32_t b) {
  uint32_t d;
  asm("max.bf16x2 %0, %1, %2;" : "=r"(d) : "r"(a), "r"(b));
  return d;
}
__device__ __forceinline__ void softmax_two(const float (&l)[2][2], uint32_t& p0, uint32_t& p1) {
  constexpr float kScale = 0.22360679774997896f, kLog2e = 1.4426950408889634f;
  const uint32_t r0 = pack2(l[0][0], l[1][0]), r1 = pack2(l[0][1], l[1][1]);
  const uint32_t x0 = pack2(bf_lo(r0) * kScale, bf_hi(r0) * kScale), x1 = pack2(bf_lo(r1) * kScale, bf_hi(r1) * kScale);
  uint32_t m = bmax(x0, x1);
  m = bmax(m, __shfl_xor_sync(0xffffffffu, m, 1));
  m = bmax(m, __shfl_xor_sync(0xffffffffu, m, 2));
  const float m0 = bf_lo(m) * kLog2e, m1 = bf_hi(m) * kLog2e;
  p0 = pack2(ex2(bf_lo(x0) * kLog2e - m0), ex2(bf_lo(x1) * kLog2e - m0));
  p1 = pack2(ex2(bf_hi(x0) * kLog2e - m1), ex2(bf_hi(x1) * kLog2e - m1));
}

__device__ __forceinline__ void halo_read(uint32_t (&kpv)[10], uint32_t (&vpv)[10], uint32_t (&tg)[7], const uint4* hp) {
#pragma unroll
  for (int j = 0; j < 7; j++) {
    uint32_t x0, x1, x2;
    asm volatile("ld.relaxed.gpu.global.v4.u32 {%0, %1, %2, %3}, [%4];"
                 : "=r"(x0), "=r"(x1), "=r"(x2), "=r"(tg[j]) : "l"(hp + 32 * j) : "memory");
    if (j < 4) kpv[3 * j] = x0; else vpv[3 * j - 10] = x0;
    if (j < 3) kpv[3 * j + 1] = x1; else vpv[3 * j - 9] = x1;
    if (j < 3) kpv[3 * j + 2] = x2; else if (j < 6) vpv[3 * j - 8] = x2;
  }
}

template <int ROT>
__device__ __forceinline__ void pack_qkv(const float* acc, uint32_t (&qlo)[10], uint32_t (&qhi)[10], uint32_t (&klo)[10],
                                         uint32_t (&khi)[10], uint32_t (&vlo)[10], uint32_t (&vhi)[10]) {
#pragma unroll
  for (int j = 0; j < 10; j++) {
    const int x = (j + ROT) % 10, tq = x < 8 ? x : 16 + x, tk = x < 8 ? 8 + x : 18 + x, tv = x < 8 ? 16 + x : 20 + x;
    khi[j] = pack2(acc[4 * tk + 2], acc[4 * tk + 3]);
    vhi[j] = movm(pack2(acc[4 * tv + 2], acc[4 * tv + 3]));
    qlo[j] = pack2(acc[4 * tq], acc[4 * tq + 1]);
    qhi[j] = pack2(acc[4 * tq + 2], acc[4 * tq + 3]);
    klo[j] = pack2(acc[4 * tk], acc[4 * tk + 1]);
    vlo[j] = pack2(acc[4 * tv], acc[4 * tv + 1]);
    asm volatile("" : "+r"(khi[j]), "+r"(qlo[j]), "+r"(qhi[j]), "+r"(klo[j]), "+r"(vlo[j]));
  }
}

template <int ROT> __device__ __forceinline__ void halo_send(const float* acc, uint4* ho, uint32_t tag) {
#pragma unroll
  for (int j = 0; j < 7; j++) {
    uint32_t x[3];
#pragma unroll
    for (int e = 0; e < 3; e++) {
      const int i = 3 * j + e, y = (i % 10 + ROT) % 10, tk = y < 8 ? 8 + y : 18 + y, tv = y < 8 ? 16 + y : 20 + y;
      x[e] = i < 10 ? pack2(acc[4 * tk + 2], acc[4 * tk + 3]) : i < 20 ? movm(pack2(acc[4 * tv + 2], acc[4 * tv + 3])) : 0u;
    }
    asm volatile("st.relaxed.gpu.global.v4.u32 [%0], {%1, %2, %3, %4};" ::"l"(ho + 32 * j), "r"(x[0]), "r"(x[1]), "r"(x[2]), "r"(tag) : "memory");
  }
}

__device__ __forceinline__ void attention(float* acc, uint32_t sb, int b, int par, int w, int lane, uint32_t tag) {
  const int g = lane >> 2, t = lane & 3;
  uint32_t klo[10], khi[10], vlo[10], vhi[10], qlo[10], qhi[10], kpv[10], vpv[10];
  if (w == 3 && b < NCTA - 8) {
    uint4* ho = g_halo + (b * 2 + par) * 224 + lane;
    if (tail_first(b & 7)) halo_send<8>(acc, ho, tag);
    else halo_send<0>(acc, ho, tag);
    TSIF(par == 0, 76);
    pin<120>(acc);
  }
  if (tail_first(b & 7)) pack_qkv<8>(acc, qlo, qhi, klo, khi, vlo, vhi);
  else pack_qkv<0>(acc, qlo, qhi, klo, khi, vlo, vhi);
  const uint32_t xa = sb + OFF_KVX + (par * 3) * 2560 + lane * 16;
  if (w < 3) {
    sts128(xa + w * 2560, khi[0], khi[1], khi[2], khi[3]);
    sts128(xa + w * 2560 + 512, khi[4], khi[5], khi[6], khi[7]);
    sts128(xa + w * 2560 + 1024, khi[8], khi[9], vhi[0], vhi[1]);
    sts128(xa + w * 2560 + 1536, vhi[2], vhi[3], vhi[4], vhi[5]);
    sts128(xa + w * 2560 + 2048, vhi[6], vhi[7], vhi[8], vhi[9]);
  }
  TSIF(par == 0 && w == 1, 64);
#pragma unroll
  for (int j = 0; j < 10; j++) vlo[j] = movm(vlo[j]);
  const bool far0 = 2 * t > g, far1 = 2 * t + 1 > g;
  const uint32_t mfar = (far0 ? 0x0000FFFFu : 0u) | (far1 ? 0xFFFF0000u : 0u);
  float slo[4][2], lg[2][2];
  uint32_t phi[4], plo[4], qml[4], qmh[4];
#pragma unroll
  for (int h = 0; h < 4; h++) {
    const int f = h == 0 ? 0 : h == 1 ? 3 : h == 2 ? 5 : 8, hf = h < 2 ? 2 : 7;
    const bool mine = (h & 1) ? t >= 2 : t < 2;
    qml[h] = mine ? qlo[hf] : 0u;
    qmh[h] = mine ? qhi[hf] : 0u;
    float a[4] = {0.f, 0.f, 0.f, 0.f}, c[4] = {0.f, 0.f, 0.f, 0.f};
    mma16816(a, qlo[f], qhi[f], qlo[f + 1], qhi[f + 1], klo[f], klo[f + 1]);
    mma16816(c, qlo[f], qhi[f], qlo[f + 1], qhi[f + 1], khi[f], khi[f + 1]);
    mma1688(a, qml[h], qmh[h], klo[hf]);
    mma1688(c, qml[h], qmh[h], khi[hf]);
    slo[h][0] = a[0];
    slo[h][1] = a[1];
    lg[h & 1][0] = far0 ? a[2] : c[2];
    lg[h & 1][1] = far1 ? a[3] : c[3];
    if (h & 1) softmax_two(lg, phi[h - 1], phi[h]);
  }
  TSIF(par == 0 && w == 1, 65);
  wg_sync(1 + par);
  TSIF(par == 0 && w == 1, 66);
  const bool nohist = (w == 0) && (b < 8);
  const uint4* hp = g_halo + ((b - 8) * 2 + par) * 224 + lane;
  uint32_t tg[7];
  if (w > 0) {
    const uint4 v0 = lds128(xa + (w - 1) * 2560), v1 = lds128(xa + (w - 1) * 2560 + 512), v2 = lds128(xa + (w - 1) * 2560 + 1024);
    const uint4 v3 = lds128(xa + (w - 1) * 2560 + 1536), v4 = lds128(xa + (w - 1) * 2560 + 2048);
    kpv[0] = v0.x; kpv[1] = v0.y; kpv[2] = v0.z; kpv[3] = v0.w; kpv[4] = v1.x; kpv[5] = v1.y; kpv[6] = v1.z; kpv[7] = v1.w;
    kpv[8] = v2.x; kpv[9] = v2.y; vpv[0] = v2.z; vpv[1] = v2.w; vpv[2] = v3.x; vpv[3] = v3.y; vpv[4] = v3.z; vpv[5] = v3.w;
    vpv[6] = v4.x; vpv[7] = v4.y; vpv[8] = v4.z; vpv[9] = v4.w;
  } else if (nohist) {
#pragma unroll
    for (int j = 0; j < 10; j++) kpv[j] = vpv[j] = 0u;
  } else {
    TSIF(par == 0, 77);
    halo_read(kpv, vpv, tg, hp);
  }
  if (w == 0 && !nohist) {
    int spins = 0;
    while (true) {
      bool ok = true;
#pragma unroll
      for (int j = 0; j < 7; j++) ok = ok && tg[j] == tag;
      if (__all_sync(0xffffffffu, ok) || ++spins > SPIN_LIMIT) break;
      halo_read(kpv, vpv, tg, hp);
    }
    TSIF(par == 0, 79);
  }
#pragma unroll
  for (int h = 0; h < 4; h++) {
    const int f = h == 0 ? 0 : h == 1 ? 3 : h == 2 ? 5 : 8, hf = h < 2 ? 2 : 7;
    float a[4] = {0.f, 0.f, 0.f, 0.f};
    mma16816(a, qlo[f], qhi[f], qlo[f + 1], qhi[f + 1], kpv[f], kpv[f + 1]);
    mma1688(a, qml[h], qmh[h], kpv[hf]);
    const float ninf = __int_as_float(0xff800000);
    lg[h & 1][0] = far0 ? (nohist ? ninf : a[0]) : slo[h][0];
    lg[h & 1][1] = far1 ? (nohist ? ninf : a[1]) : slo[h][1];
    if (h & 1) softmax_two(lg, plo[h - 1], plo[h]);
  }
  TSIF(par == 0 && w <= 1, 67 + w);
  uint32_t ov[20];
#pragma unroll
  for (int hp = 0; hp < 2; hp++) {
    const int hf = hp ? 7 : 2;
    float sh[4] = {0.f, 0.f, 0.f, 0.f}, i0 = 0.f, i1 = 0.f;
#pragma unroll
    for (int e = 0; e < 2; e++) {
      const int h = 2 * hp + e, f = h == 0 ? 0 : h == 1 ? 3 : h == 2 ? 5 : 8;
      const uint32_t a0 = plo[h] & mfar, a2 = plo[h] & ~mfar, a3 = phi[h] & mfar, c1 = phi[h] & ~mfar;
      float sum[4] = {0.f, 0.f, 0.f, 0.f};
      mma1688(sum, plo[h], phi[h], 0x3F803F80u);
      const float r0 = rcp(sum[0]), r1 = rcp(sum[2]);
#pragma unroll
      for (int j = f; j < f + 2; j++) {
        float o[4] = {0.f, 0.f, 0.f, 0.f};
        mma16816(o, a0, 0u, a2, a3, vpv[j], vlo[j]);
        mma1688(o, 0u, c1, vhi[j]);
        ov[2 * j] = pack2(o[0] * r0, o[1] * r0);
        ov[2 * j + 1] = pack2(o[2] * r1, o[3] * r1);
      }
      const bool mine = e ? g >= 4 : g < 4;
      mma16816(sh, a0, 0u, a2, a3, mine ? vpv[hf] : 0u, mine ? vlo[hf] : 0u);
      mma1688(sh, 0u, c1, mine ? vhi[hf] : 0u);
      if (e == 0 || t >= 2) {
        i0 = r0;
        i1 = r1;
      }
    }
    ov[2 * hf] = pack2(sh[0] * i0, sh[1] * i0);
    ov[2 * hf + 1] = pack2(sh[2] * i1, sh[3] * i1);
  }
  TS(32 + 4 * par + w);
  mbar_wait(sb + OFF_BAR + 8 * B_P1, 0);
  const uint32_t oa = sb + OFF_OA + (lane >> 4) * 2048 + (32 * w + 2 * (lane & 15) + par) * 16;
#pragma unroll
  for (int j = 0; j < 5; j++) stsm4(oa + 4096 * j, ov + 4 * j);
  TSIF(par == 0 && w == 0, 120);
  fence_async_smem();
  TSIF(par == 0 && w == 0, 121);
  __syncwarp();
  if (lane == 0) mbar_arrive(sb + OFF_BAR + 8 * B_ATTN);
  TSM(w == 0 || w == 2, 122 + par + (w == 2 ? 3 : 0));
}

struct Maps {
  CUtensorMap x, wm, wt, k, v, y, wo, qm, qt, om, ot, yl, ol;
};

__device__ __forceinline__ void load_stage(uint32_t sb, int kb, int b, const Maps& m) {
  const uint32_t st = sb + (kb & 3) * STAGE_BYTES, bar = sb + OFF_BAR + 8 * (B_FULL1 + (kb & 3));
  const int r = b >> 3, hg = b & 7, slab = kb - KV_KB;
  const bool kv = slab >= 0 && slab < 5;
  const uint32_t kbar = sb + OFF_BAR + 8 * (B_KV + slab), dst = sb + OFF_KVS + slab * KVS_BYTES;
  mbar_expect_tx(bar, STAGE_BYTES);
  if (kv) mbar_expect_tx(kbar, KVS_BYTES);
  tma_3d(st, &m.x, 64 * kb, 64 * r, 0, bar);
  tma_3d(st + ST_W, &m.wm, 80 * hg + (tail_first(hg) ? 16 : 0), 64 * kb, 0, bar);
  tma_3d(st + ST_WT, &m.wt, 80 * hg + (tail_first(hg) ? 0 : 64), 64 * kb, 0, bar);
  if (kv) tma_3d(dst, &m.k, 0, 32 * (b >> 1) - 3, 2 * slab + (b & 1), kbar);
  if (kv) tma_3d(dst + KVS_V, &m.v, 0, 32 * (b >> 1), 2 * slab + (b & 1), kbar);
}

__global__ void __launch_bounds__(NTHR, 1) fused_kernel(const __grid_constant__ Maps m, const Params p) {
  extern __shared__ __align__(1024) uint8_t smem[];
  const uint32_t sb = (uint32_t)__cvta_generic_to_shared(smem);
  const uint32_t bars = sb + OFF_BAR;
  const int tid = threadIdx.x, lane = tid & 31;
  int b = blockIdx.x;
  b = (((b & 63) >> 3) * 2 + (b & 1)) * 8 + (((b < 64 ? 0x6521 : 0x7430) >> (4 * ((b >> 1) & 3))) & 7);
  const int r = b >> 3, hg = b & 7;

  if (tid == T_ISSUE) {
    TSM(true, 0);
    mbar_init(bars + 8 * B_F0, 1);
    fence_async_smem();
    mbar_expect_tx(bars + 8 * B_F0, ST_WT);
    tma_3d(sb, &m.x, 0, 64 * r, 0, bars + 8 * B_F0);
    tma_3d(sb + ST_W, &m.wm, 80 * hg + (tail_first(hg) ? 16 : 0), 0, 0, bars + 8 * B_F0);
#pragma unroll
    for (int i = 0; i < 4; i++) mbar_init(bars + 8 * (B_FULL1 + i), 1);
    fence_async_smem();
    mbar_expect_tx(bars + 8 * B_FULL1, STAGE_BYTES - ST_WT);
    tma_3d(sb + ST_WT, &m.wt, 80 * hg + (tail_first(hg) ? 0 : 64), 0, 0, bars + 8 * B_FULL1);
    load_stage(sb, 1, b, m);
  } else if (tid == T_INIT) {
#pragma unroll
    for (int i = 0; i < B_F0; i++) mbar_init(bars + 8 * i, i < B_GATE ? 8 : i < B_CVD ? 4 : i == B_CVD ? 20 : 1);
    fence_async_smem();
  }
  const int warp = __shfl_sync(0xffffffffu, tid >> 5, 0), wg = warp >> 2, w = warp & 3;
  __syncthreads();

  if (wg == 3) {
    asm volatile("setmaxnreg.dec.sync.aligned.u32 56;");
    if (w == 0) {
      if (lane == 0) {
#pragma unroll 1
        for (int kb = 2; kb < 10; kb++) {
          if (kb >= 4) mbar_wait(bars + 8 * (kb == 7 ? B_E3 : B_EMPTY1 + (kb & 3)), (kb >> 3) & 1);
          TSIF(kb >= 4, 44 + kb);
          load_stage(sb, kb, b, m);
          TSIF(kb == 3, 60);
          if (kb == 9) mbar_arrive(bars + 8 * B_LAST);
        }
        mbar_wait(bars + 8 * B_WOP, 0);
        mbar_wait(bars + 8 * B_EPOCH, 0);
        flag_wait(g_cnt + C_W + 32 * hg, (lds32(sb + OFF_EPOCH) + 1) * 16);
        TS(30);
#pragma unroll 1
        for (int j = 0; j < 8; j++) {
          if (j >= 6) mbar_wait(bars + 8 * (B_EMPTY2 + j - 6), 0);
          if (j == 4) mbar_wait(bars + 8 * B_ORB, 0);
          TSIF(j >= 6, 100 + j);
          mbar_expect_tx(bars + 8 * (B_FULL2 + j), j == 0 ? WO_BYTES : j == 5 ? O_BYTES + WO_BYTES + 512 : O_BYTES + WO_BYTES);
          bulk_load(sb + off_w(j), g_WO + (hg * 8 + step_src(hg, j)) * 800, WO_BYTES, bars + 8 * (B_FULL2 + j));
        }
        mbar_wait(bars + 8 * (B_EMPTY2 + 3), 0);
        mbar_expect_tx(bars + 8 * B_QF, O_BYTES);
        tma_2d(sb + OFF_QS, &m.qm, 80 * hg, 128 * r, bars + 8 * B_QF);
        tma_2d(sb + OFF_QT, &m.qt, 80 * hg + 64, 128 * r, bars + 8 * B_QF);
      }
    } else if (w == 1) {
      unsigned epoch = 0;
      if (lane == 0) {
        epoch = atomicAdd(g_cnt + C_LAUNCH, 1u) / NCTA;
        asm volatile("st.shared.u32 [%0], %1;" ::"r"(sb + OFF_EPOCH), "r"(epoch) : "memory");
        mbar_arrive(bars + 8 * B_EPOCH);
        mbar_wait(bars + 8 * B_KVD, 0);
        mbar_expect_tx(bars + 8 * B_HB, 5 * 4096);
#pragma unroll 1
        for (int c = 0; c < 5; c++) {
          if (c == 3) mbar_wait(bars + 8 * B_S3, 0);
          bulk_load(sb + off_ch(c) + U_BYTES, p.ssm_k + (5 * b + c) * SEQ, 4096, bars + 8 * B_HB);
        }
#pragma unroll
        for (int c = 0; c < 4; c++) mbar_expect_tx(bars + 8 * (B_U + c), c < 3 ? U_BYTES : 2 * U_BYTES);
        const uint4* usrc = g_U + 5 * b * U_PITCH;
        mbar_wait(bars + 8 * B_USIG, 0);
        flag_wait(g_cnt + C_PREP + 32 * (b & 15), (epoch + 1) * NCTA);
        TS(23);
#pragma unroll
        for (int c = 0; c < 5; c++) {
          if (c == 3) mbar_wait(bars + 8 * (B_U + 2), 0);
          bulk_load(sb + off_ch(c), usrc + c * U_PITCH, U_BYTES, bars + 8 * (B_U + (c < 3 ? c : 3)));
          TSIF(c == 0 || c == 4, 116 + (c >> 2));
        }
      }
      epoch = __shfl_sync(0xffffffffu, epoch, 0);
      if (lane < 8) {
        const int src = (b & ~7) | step_src(hg, lane);
        mbar_wait(bars + 8 * B_ATTN, 0);
        TS(20);
        bool seen = false;
#pragma unroll 1
        for (int spins = 0; spins < SPIN_LIMIT; spins++) {
          const bool now = !seen && (int)(flag_read(g_cnt + C_O + 32 * src) - (epoch + 1)) >= 0;
          if (now && lane >= 1 && lane < 4) bulk_load(sb + off_o(lane), g_O + src * 1280, O_BYTES, bars + 8 * (B_FULL2 + lane));
          seen = seen || now;
          if (__all_sync(0xff, seen)) break;
        }
        TS(21);
        if (lane == 5) bulk_load(sb + OFF_GATE, g_gate + 128 * r, 512, bars + 8 * (B_FULL2 + 5));
#pragma unroll 1
        for (int j = 4; j < 8; j++) {
          if (lane == j) {
            mbar_wait(bars + 8 * (j < 6 ? B_C34 : B_EMPTY2 + j - 6), 0);
            bulk_load(sb + off_o(j), g_O + src * 1280, O_BYTES, bars + 8 * (B_FULL2 + j));
          }
          __syncwarp(0xff);
        }
        TS(22);
      }
    } else if (w == 2) {
      mbar_wait(bars + 8 * B_PREP, 0);
      flag_signal(g_cnt + C_PREP, 16, lane);
      TS(25);
      if (lane == 0) {
        mbar_arrive(bars + 8 * B_USIG);
        mbar_expect_tx(bars + 8 * B_ORB, O_BYTES / 4 + 64);
        mbar_wait(bars + 8 * B_GATE, 0);
        publish(g_gate + 16 * b, sb + OFF_GATE + 64 * hg, 64);
        bulk_load(sb + OFF_GATE + 64 * hg, g_gate + 16 * b, 64, bars + 8 * B_ORB);
        mbar_wait(bars + 8 * B_ATTN, 0);
        publish(g_O + b * 1280, sb + OFF_OA, O_BYTES);
        tma_2d(sb + OFF_KVX + 10240, &m.ol, 48, b * 160, bars + 8 * B_ORB);
        TS(74);
        mbar_wait(bars + 8 * B_ORB, 0);
        flag_bump(g_cnt + C_O + 32 * b);
        TS(26);
      }
    } else {
      if (lane == 0) {
        uint4* dst = g_WO + (hg * 8 + (r >> 1)) * 800 + (r & 1) * 80;
        mbar_wait(bars + 8 * B_S3, 0);
        asm volatile("cp.async.bulk.prefetch.L2.global [%0], 6400;" ::"l"(p.wo + b * 3200) : "memory");
        mbar_wait(bars + 8 * B_P1, 0);
        mbar_wait(bars + 8 * WB_TRIG, 0);
        mbar_expect_tx(bars + 8 * B_WST, WO_BYTES / 2);
        tma_3d(sb + OFF_WA, &m.wo, 0, 40 * r, 5 * hg, bars + 8 * B_WST);
        mbar_wait(bars + 8 * B_WST, 0);
#pragma unroll 1
        for (int n = 0; n < 5; n++) bulk_store(dst + 160 * n, sb + OFF_WA + 1280 * n, 1280);
        bulk_wait_read();
        mbar_expect_tx(bars + 8 * B_WST, WO_BYTES / 2);
#pragma unroll 1
        for (int n = 0; n < 5; n++) bulk_load(sb + OFF_WA + 1280 * n, dst + 160 * n, 1280, bars + 8 * B_WST);
        mbar_wait(bars + 8 * B_WST, 1);
        flag_bump(g_cnt + C_W + 32 * hg);
        mbar_arrive(bars + 8 * B_WOP);
        TS(71);
        mbar_expect_tx(bars + 8 * B_C34, 3 * (U_BYTES / 4));
        mbar_expect_tx(bars + 8 * B_YRB, 2 * (U_BYTES / 4));
#pragma unroll 1
        for (int c = 0; c < 5; c++) {
          mbar_wait(bars + 8 * (B_YST + c), 0);
          publish(g_U + (5 * b + c) * U_PITCH, sb + off_ch(c), U_BYTES);
          tma_2d(sb + off_ch(c), &m.yl, 48, (5 * b + c) * (U_PITCH / 8), bars + 8 * (c < 3 ? B_C34 : B_YRB));
        }
        TS(75);
        mbar_wait(bars + 8 * B_C34, 0);
        mbar_wait(bars + 8 * B_YRB, 0);
        flag_bump(g_cnt + C_Y + 32 * (b >> 4));
        TS(27);
        mbar_expect_tx(bars + 8 * B_YFULL, 20480);
        flag_wait(g_cnt + C_Y + 32 * hg, (lds32(sb + OFF_EPOCH) + 1) * 16);
        TS(24);
        tma_2d(sb + OFF_YT, &m.y, 128 * r, 80 * hg, bars + 8 * B_YFULL);
        tma_2d(sb + OFF_YT + 10240, &m.y, 128 * r + 64, 80 * hg, bars + 8 * B_YFULL);
      }
    }
  } else {
    asm volatile("setmaxnreg.inc.sync.aligned.u32 152;");
    if (wg < 2) {
      float acc[120];
#pragma unroll
      for (int i = 0; i < 120; i++) acc[i] = 0.f;
      const uint32_t da = desc_lo(sb + wg * 8192, 16), db = desc_lo(sb + ST_W, 8192), dc = desc_lo(sb + ST_WT, 2048);
      mbar_wait(bars + 8 * B_F0, 0);
      TSIF(w == 0 && wg == 0, 1);
      wg_fence();
#pragma unroll
      for (int k = 0; k < 4; k++) WgSST<192>::mma<HI_SW128, HI_SW128>(acc, da + 2 * k, db + 128 * k, 1);
      wg_commit();
      mbar_wait(bars + 8 * B_FULL1, 0);
      wg_fence();
#pragma unroll
      for (int k = 0; k < 4; k++) WgSST<48>::mma<HI_SW128, HI_SW32>(acc + 96, da + 2 * k, dc + 32 * k, 1);
      wg_commit();
#pragma unroll 1
      for (int kb = 1; kb < 10; kb++) {
        mbar_wait(bars + 8 * (B_FULL1 + (kb & 3)), (kb >> 2) & 1);
        const uint32_t so = (kb & 3) * (STAGE_BYTES >> 4);
        wg_fence();
#pragma unroll
        for (int k = 0; k < 4; k++) {
          WgSST<192>::mma<HI_SW128, HI_SW128>(acc, da + so + 2 * k, db + so + 128 * k, 1);
          WgSST<48>::mma<HI_SW128, HI_SW32>(acc + 96, da + so + 2 * k, dc + so + 32 * k, 1);
        }
        wg_commit();
        wg_wait<1>();
        if (lane == 0) mbar_arrive(bars + 8 * (kb == 4 ? B_E3 : B_EMPTY1 + ((kb - 1) & 3)));
      }
      mbar_wait(bars + 8 * B_EPOCH, 0);
      const uint32_t tag = lds32(sb + OFF_EPOCH) + 1;
      mbar_wait(bars + 8 * B_S3, 0);
      wg_wait<0>();
      pin<120>(acc);
      if (lane == 0) mbar_arrive(bars + 8 * B_P1);
      TSM(w == 0, 3 + wg);
      attention(acc, sb, b, wg, w, lane, tag);
    } else {
      const int tw = tid & 127, chl = 64 * (b & 1) + 8 * w + (lane >> 2);
      uint4* up = g_U + chl * U_PITCH + ((4 * (b >> 1) + (lane & 3)) ^ ((b >> 2) & 1));
      uint2 sw[10];
      uint32_t dv = 0;
      if (lane < 5) dv = __ldg(reinterpret_cast<const unsigned short*>(p.ssm_D) + 5 * b + lane);
#pragma unroll
      for (int i = 0; i < 10; i++) sw[i] = ldg64(reinterpret_cast<const uint2*>(p.shift_k) + chl + 128 * (i >> 1) + 32 * (i & 1));
      uint32_t tab[12];
      uint32_t tt[2];
      fft_tables(tab, tw);
      fft_twiddles(tt, tw);
      uint4 res[10];
#pragma unroll
      for (int i = 0; i < 10; i++) res[i] = make_uint4(0, 0, 0, 0);
#pragma unroll 1
      for (int slab = 0; slab < 5; slab++) {
#pragma unroll
        for (int i = 0; i < 8; i++) res[i] = res[i + 2];
        prep_slab(res + 8, sw, sb, slab, w, lane);
        TSIF(w == 0, 99 + 4 * slab);
#pragma unroll
        for (int i = 0; i < 8; i++) sw[i] = sw[i + 2];
      }
      TSIF(w == 0, 28);
      __syncwarp();
      if (lane == 0) mbar_arrive(bars + 8 * B_KVD + ((res[8].x ^ res[9].x) & p.zero));
      mbar_wait(bars + 8 * B_KVD, 0);
      fft_tables_store(tab, sb, tw);
      mbar_wait(bars + 8 * B_LAST, 0);
#pragma unroll
      for (int i = 0; i < 10; i++) up[(128 * (i >> 1) + 32 * (i & 1)) * U_PITCH] = res[i];
      __syncwarp();
      if (lane == 0) mbar_arrive(bars + 8 * B_PREP);
      TSIF(w == 0, 5);
      mbar_wait(bars + 8 * B_LAST, 0);
      prep_gate(p, sb, b, w, lane);
      __syncwarp();
      if (lane == 0) mbar_arrive(bars + 8 * B_GATE);
      TSIF(w == 0, 72);
      mbar_wait(bars + 8 * B_HB, 0);
      TSIF(w == 0, 2);
      const uint32_t ha = sb + U_BYTES + ((tw >> 3) * 16 + 8 + (tw & 7)) * 16;
      uint4 hv[5];
#pragma unroll
      for (int c = 0; c < 5; c++) hv[c] = lds128(ha + off_ch(c));
      __syncwarp();
#pragma unroll
      for (int c = 0; c < 5; c++) sts128((ha ^ 16) + off_ch(c), hv[c].x, hv[c].y, hv[c].z, hv[c].w);
      asm volatile("st.shared.v2.u32 [%0], {%1, %2};" ::"r"(sb + OFF_TT + 8 * tw), "r"(tt[0]), "r"(tt[1]) : "memory");
      if (tw < 5) asm volatile("st.shared.f32 [%0], %1;" ::"r"(sb + OFF_D + 4 * tw), "f"(bf_lo(dv) * 0.125f) : "memory");
      fence_async_smem();
      __syncwarp();
      if (lane == 0) mbar_arrive(bars + 8 * B_HA);
      TSIF(w == 0, 6);
    }

    FftConst fc;
    TSM(w == 0 && wg == 0, 104);
    mbar_wait(bars + 8 * B_HA, 0);
    fft_matrices(fc, sb, w, lane);
    TSM(w == 0 && wg == 0, 105);
    TSM(w == 0 && wg == 2, 124);
#pragma unroll 1
    for (uint32_t tasks = wg == 0 ? TASK0 : wg == 1 ? TASK1 : TASK2; tasks; tasks >>= 4) {
      const int c = (tasks & 7) - 1;
      conv_channel(fc, sb, c, wg, w, lane);
      if (lane == 0) mbar_arrive(bars + 8 * (B_YST + c));
      TSM(w == 0, 10 + c);
    }

    if (wg != 1) {
      const int wg = warp >> 3;
      const int g = lane >> 2;
      float acc[40];
#pragma unroll
      for (int i = 0; i < 40; i++) acc[i] = 0.f;
      const uint32_t da = desc_lo(sb + wg * 1024, 2048), db = desc_lo(sb, 2560);
      mbar_wait(bars + 8 * B_ORB, 0);
      mbar_wait(bars + 8 * B_FULL2, 0);
      TSM(w == 0, 15 + wg);
#pragma unroll 1
      for (int j = 0; j < 8; j++) {
        if (j == 1 - wg) mbar_wait(bars + 8 * B_CVD, 0);
        mbar_wait(bars + 8 * (B_FULL2 + j), 0);
        TSM(w == 0 && wg == 0, 44 + (j < 4 ? j : j + 6));
        const uint32_t oa = da + (off_o(j) >> 4), ob = db + (off_w(j) >> 4);
        wg_fence();
#pragma unroll
        for (int k = 0; k < 5; k++) WgSST<80>::mma<HI_NONE, HI_SW32>(acc, oa + 256 * k, ob + 32 * k, 1);
        wg_commit();
        wg_wait<1>();
        if (j >= 1 && j <= 4 && lane == 0) mbar_arrive(bars + 8 * (B_EMPTY2 + j - 1));
      }
      TSIF(w == 0 && wg == 0, 113);
      const int tr = 64 * wg + 16 * w + (lane & 15);
      const uint32_t fm = sb + OFF_QS + tr * 128, fx = (lane >> 4) ^ (tr & 7);
      const uint32_t ft = sb + OFF_QT + tr * 32 + (((lane >> 4) ^ (tr >> 2)) & 1) * 16;
      const float g0 = __uint_as_float(lds32(sb + OFF_GATE + (64 * wg + 16 * w + g) * 4));
      const float g1 = __uint_as_float(lds32(sb + OFF_GATE + (64 * wg + 16 * w + 8 + g) * 4));
      const uint32_t ga = pack2(g0, g0), gb = pack2(g1, g1);
      const uint32_t na = pack2(1.f - g0, 1.f - g0), nb = pack2(1.f - g1, 1.f - g1);

      uint32_t qf[20];
      mbar_wait(bars + 8 * B_QF, 0);
      TSM(w == 0 && wg == 0, 99);
#pragma unroll
      for (int j = 0; j < 5; j++) ldsm4(qf + 4 * j, j < 4 ? fm + ((fx ^ (2 * j)) << 4) : ft);
#pragma unroll
      for (int i = 0; i < 20; i++) {
        qf[i] = bmul((i & 1) ? gb : ga, qf[i]);
        asm volatile("" : "+r"(qf[i]));
      }

      wg_wait<0>();
      pin<40>(acc);
      TSM(w == 0, 17 + wg);
      uint32_t pb[20];
#pragma unroll
      for (int j = 0; j < 10; j++) {
        pb[2 * j] = bmul(na, pack2(acc[4 * j], acc[4 * j + 1]));
        pb[2 * j + 1] = bmul(nb, pack2(acc[4 * j + 2], acc[4 * j + 3]));
        asm volatile("" : "+r"(pb[2 * j]), "+r"(pb[2 * j + 1]));
      }
      const uint32_t ya = sb + OFF_YT + wg * 10240 + ((lane >> 4) * 8 + (lane & 7)) * 128 +
                          (((2 * w + (((lane >> 3) & 1) ^ wg)) ^ (lane & 7)) << 4);
      mbar_wait(bars + 8 * B_YFULL, 0);
      TSM(w == 0 && wg == 0, 19);
#pragma unroll
      for (int j = 0; j < 5; j++) {
        uint32_t y[4];
        ldsm4t(y, ya + 2048 * j);
#pragma unroll
        for (int i = 0; i < 4; i++)
          qf[4 * j + i] = bfma(qf[4 * j + i], y[i], pb[4 * j + i]);
      }
#pragma unroll
      for (int j = 0; j < 5; j++) stsm4(j < 4 ? fm + ((fx ^ (2 * j)) << 4) : ft, qf + 4 * j);
      fence_async_smem();
      __syncwarp();
      if (lane == 0) {
        const int row = 64 * wg + 16 * w;
        asm volatile("cp.async.bulk.tensor.2d.global.shared::cta.bulk_group [%0, {%2, %3}], [%1];"
                     ::"l"(&m.om), "r"(sb + OFF_QS + row * 128), "r"(80 * hg), "r"(128 * r + row) : "memory");
        asm volatile("cp.async.bulk.tensor.2d.global.shared::cta.bulk_group [%0, {%2, %3}], [%1];"
                     ::"l"(&m.ot), "r"(sb + OFF_QT + row * 32), "r"(80 * hg + 64), "r"(128 * r + row) : "memory");
        asm volatile("cp.async.bulk.commit_group;\ncp.async.bulk.wait_group.read 0;" ::: "memory");
      }
      TSM(w == 0 || w == 3, 40 + 2 * wg + (w & 1));
    }
  }
}

typedef CUresult (*EncodeFn)(CUtensorMap*, CUtensorMapDataType, cuuint32_t, void*, const cuuint64_t*, const cuuint64_t*,
                             const cuuint32_t*, const cuuint32_t*, CUtensorMapInterleave, CUtensorMapSwizzle,
                             CUtensorMapL2promotion, CUtensorMapFloatOOBfill);

void encode(EncodeFn fn, CUtensorMap* tm, const void* base, int rank, const cuuint64_t* dims, const cuuint64_t* strides,
            const cuuint32_t* box, CUtensorMapSwizzle swz) {
  const cuuint32_t ones[3] = {1, 1, 1};
  fn(tm, CU_TENSOR_MAP_DATA_TYPE_BFLOAT16, rank, const_cast<void*>(base), dims, strides, box, ones,
     CU_TENSOR_MAP_INTERLEAVE_NONE, swz, CU_TENSOR_MAP_L2_PROMOTION_L2_128B, CU_TENSOR_MAP_FLOAT_OOB_FILL_NONE);
}

}

extern "C" void kernel_launch(void* const* d_in, const int* in_sizes, int n_in, void* d_out, int out_size) {
  (void)in_sizes; (void)n_in; (void)out_size;
  Params p;
  p.q = (const __nv_bfloat16*)d_in[0];
  p.k = (const __nv_bfloat16*)d_in[1];
  p.v = (const __nv_bfloat16*)d_in[2];
  p.shift_k = (const __nv_bfloat16*)d_in[3];
  p.ssm_k = (const __nv_bfloat16*)d_in[4];
  p.ssm_D = (const __nv_bfloat16*)d_in[5];
  p.wqkv = (const __nv_bfloat16*)d_in[7];
  p.wo = (const __nv_bfloat16*)d_in[8];
  p.gate_w = (const __nv_bfloat16*)d_in[9];
  p.out = (__nv_bfloat16*)d_out;
  p.zero = 0;

  static EncodeFn fn = nullptr;
  static void *yaddr = nullptr, *oaddr = nullptr;
  if (!fn) {
    cudaDriverEntryPointQueryResult qr;
    void* f = nullptr;
    cudaGetDriverEntryPoint("cuTensorMapEncodeTiled", &f, cudaEnableDefault, &qr);
    fn = (EncodeFn)f;
    cudaGetSymbolAddress(&yaddr, g_U);
    cudaGetSymbolAddress(&oaddr, g_O);
    cudaFuncSetAttribute(fused_kernel, cudaFuncAttributeMaxDynamicSharedMemorySize, SMEM_BYTES);
  }
  Maps m;
  {
    const cuuint64_t dims[3] = {640, 1024, 2}, st[2] = {2560, 1280};
    const cuuint32_t box[3] = {64, 64, 2};
    encode(fn, &m.x, p.q, 3, dims, st, box, CU_TENSOR_MAP_SWIZZLE_128B);
  }
  {
    const cuuint64_t dims[3] = {640, 640, 3}, st[2] = {3840, 1280};
    const cuuint32_t box[3] = {64, 64, 3}, boxt[3] = {16, 64, 3};
    encode(fn, &m.wm, p.wqkv, 3, dims, st, box, CU_TENSOR_MAP_SWIZZLE_128B);
    encode(fn, &m.wt, p.wqkv, 3, dims, st, boxt, CU_TENSOR_MAP_SWIZZLE_32B);
  }
  {
    const cuuint64_t dims[3] = {64, 2048, 10}, st[2] = {1280, 128};
    const cuuint32_t boxk[3] = {64, 35, 1}, boxv[3] = {64, 32, 1};
    encode(fn, &m.k, p.k, 3, dims, st, boxk, CU_TENSOR_MAP_SWIZZLE_128B);
    encode(fn, &m.v, p.v, 3, dims, st, boxv, CU_TENSOR_MAP_SWIZZLE_128B);
  }
  {
    const cuuint64_t dims[3] = {16, 640, 40}, st[2] = {1280, 32};
    const cuuint32_t box[3] = {16, 40, 5};
    encode(fn, &m.wo, p.wo, 3, dims, st, box, CU_TENSOR_MAP_SWIZZLE_32B);
  }
  {
    const cuuint64_t dims[2] = {2048, 640}, st[1] = {U_PITCH * 16};
    const cuuint32_t box[2] = {64, 80};
    encode(fn, &m.y, yaddr, 2, dims, st, box, CU_TENSOR_MAP_SWIZZLE_128B);
    const cuuint64_t dl[2] = {64, DIM * U_PITCH / 8}, dol[2] = {64, NCTA * 160}, sl[1] = {128};
    const cuuint32_t bl[2] = {16, 32}, bol[2] = {16, 160};
    encode(fn, &m.yl, yaddr, 2, dl, sl, bl, CU_TENSOR_MAP_SWIZZLE_NONE);
    encode(fn, &m.ol, oaddr, 2, dol, sl, bol, CU_TENSOR_MAP_SWIZZLE_NONE);
  }
  {
    const cuuint64_t dims[2] = {640, 2048}, st[1] = {1280};
    const cuuint32_t bqm[2] = {64, 128}, bqt[2] = {16, 128}, bom[2] = {64, 16}, bot[2] = {16, 16};
    encode(fn, &m.qm, p.q, 2, dims, st, bqm, CU_TENSOR_MAP_SWIZZLE_128B);
    encode(fn, &m.qt, p.q, 2, dims, st, bqt, CU_TENSOR_MAP_SWIZZLE_32B);
    encode(fn, &m.om, p.out, 2, dims, st, bom, CU_TENSOR_MAP_SWIZZLE_128B);
    encode(fn, &m.ot, p.out, 2, dims, st, bot, CU_TENSOR_MAP_SWIZZLE_32B);
  }
  fused_kernel<<<NCTA, NTHR, SMEM_BYTES>>>(m, p);
}
```

```cpp
#include <cuda.h>
#include <cuda_bf16.h>
#include <cuda_runtime.h>
#include <stdint.h>

namespace {

constexpr int SEQ = 2048, DIM = 640, NCTA = 128, NTHR = 512;

#define KV_KB 2
#define DEV_EXIT 0
#define FENCE_LO 0
#define FENCE_HI 0
#define WB_TRIG B_USIG
#define T_ISSUE 288
#define BAD_DELAY 0
#define BAD_DELAY2 0
#define T_INIT 448
#define TASK0 0x3
#define TASK1 0x52
#define TASK2 0x41

constexpr uint32_t STAGE_BYTES = 47104, ST_W = 16384, ST_WT = 40960;
constexpr uint32_t O_BYTES = 20480, WO_BYTES = 12800;
constexpr uint32_t OFF_OA = 0;
constexpr uint32_t OFF_QS = 3 * O_BYTES, OFF_QT = OFF_QS + 16384;
constexpr uint32_t OFF_WC = 81920;
constexpr uint32_t OFF_WA = 94720;
constexpr uint32_t OFF_GATE = 145920;
constexpr uint32_t OFF_TT = 146432;
constexpr uint32_t OFF_KVX = 148480;
constexpr uint32_t OFF_CH3 = 163840;
constexpr uint32_t CH_BYTES = 12288, U_BYTES = 4096;
constexpr uint32_t OFF_FT = 225280, OFF_GT = 229376;
constexpr uint32_t OFF_CH0 = 188416;
constexpr uint32_t OFF_KVS = OFF_CH0, KVS_V = 4480, KVS_BYTES = 8576;
constexpr uint32_t OFF_YT = 163840;
constexpr uint32_t OFF_BAR = 231936;
constexpr uint32_t SMEM_BYTES = OFF_BAR + 512;

enum : uint32_t {
  B_EMPTY1 = 0, B_S3 = 3, B_E3 = 4, B_EMPTY2 = 5, B_ATTN = 9, B_P1 = 10,
  B_GATE = 11, B_HA = 12, B_KVD = 13, B_PREP = 14, B_YST = 15,
  B_CVD = 20,
  B_FULL2 = 21, B_U = 29, B_KV = 33, B_HB = 38, B_C34 = 39, B_YRB = 40, B_YFULL = 41, B_EPOCH = 42, B_LAST = 43,
  B_WOP = 44, B_USIG = 45, B_WST = 46, B_QF = 47, B_ORB = 48,
  B_F0 = 49, B_FULL1 = 50
};
constexpr uint32_t OFF_EPOCH = OFF_BAR + 8 * 58, OFF_D = OFF_BAR + 8 * 60;
__device__ __forceinline__ uint32_t off_o(int j) { return j < 4 ? OFF_OA + j * O_BYTES : j < 6 ? OFF_CH0 + (j - 4) * O_BYTES : OFF_OA + (j - 6) * O_BYTES; }
__device__ __forceinline__ uint32_t off_w(int j) { return j < 4 ? OFF_WA + j * WO_BYTES : j == 4 ? OFF_KVX : j == 5 ? OFF_WC : OFF_WA + (j - 6) * WO_BYTES; }
__device__ __forceinline__ int step_src(int hg, int j) { return j == 0 ? hg : j <= hg ? j - 1 : j; }
__device__ __forceinline__ bool tail_first(int hg) { return (hg & 3) == 3; }
__device__ __forceinline__ uint32_t off_ch(int c) { return (c < 3 ? OFF_CH0 : OFF_CH3 - 3 * CH_BYTES) + c * CH_BYTES; }

#define U_PITCH 264
__device__ __align__(1024) uint4 g_U[DIM * U_PITCH];
__device__ __align__(128) uint4 g_O[NCTA * 1280];
__device__ uint4 g_WO[64 * 800];
__device__ uint4 g_halo[NCTA * 2 * 7 * 32];
__device__ __align__(128) float g_gate[SEQ];
__device__ unsigned g_cnt[32 * (1 + 2 * 16 + 8 + NCTA)];
constexpr int C_LAUNCH = 0, C_PREP = 32, C_Y = 32 * 17, C_W = 32 * 33, C_O = 32 * 41;

#define TSM(cond, slot) do { } while (0)
#define TSIF(cond, slot) do { if (__LINE__ >= FENCE_LO && __LINE__ < FENCE_HI) sched_fence(); } while (0)
__device__ __forceinline__ void sched_fence() {
  asm volatile("{\n.reg .pred p;\n.reg .u32 c;\nmov.u32 c, %%clock;\nsetp.eq.u32 p, c, 0;\n@p st.shared.u32 [%0], c;\n}"
               ::"r"(1024 + OFF_EPOCH + 4) : "memory");
}
#define TS(slot) TSIF(true, slot)

struct Params {
  const __nv_bfloat16 *q, *k, *v, *shift_k, *ssm_k, *ssm_D, *wqkv, *wo, *gate_w;
  __nv_bfloat16* out;
  uint32_t zero;
};

constexpr int SPIN_LIMIT = 1 << 17;

__device__ __forceinline__ void mbar_init(uint32_t bar, uint32_t count) {
  asm volatile("mbarrier.init.shared::cta.b64 [%0], %1;" ::"r"(bar), "r"(count) : "memory");
}
__device__ __forceinline__ void mbar_expect_tx(uint32_t bar, uint32_t bytes) {
  asm volatile("mbarrier.arrive.expect_tx.shared::cta.b64 _, [%0], %1;" ::"r"(bar), "r"(bytes) : "memory");
}
__device__ __forceinline__ void mbar_arrive(uint32_t bar) {
  asm volatile("mbarrier.arrive.shared::cta.b64 _, [%0];" ::"r"(bar) : "memory");
}
__device__ __forceinline__ void mbar_wait(uint32_t bar, uint32_t parity) {
  uint32_t ok;
  int spins = 0;
  do {
      asm volatile("{\n.reg .pred p;\nmbarrier.try_wait.parity.shared::cta.b64 p, [%1], %2;\nselp.b32 %0, 1, 0, p;\n}"
                   : "=r"(ok) : "r"(bar), "r"(parity) : "memory");
    if (++spins > SPIN_LIMIT) break;
  } while (!ok);
}
__device__ __forceinline__ unsigned flag_read(const unsigned* p) {
  unsigned v;
  asm volatile("ld.relaxed.gpu.global.u32 %0, [%1];" : "=r"(v) : "l"(p) : "memory");
  return v;
}
__device__ __forceinline__ void flag_poll(const unsigned* p, unsigned target) {
  unsigned v;
  int spins = 0;
  do {
    asm volatile("ld.relaxed.gpu.global.u32 %0, [%1];" : "=r"(v) : "l"(p) : "memory");
    if (++spins > SPIN_LIMIT) break;
  } while ((int)(v - target) < 0);
}
__device__ __forceinline__ void flag_wait(const unsigned* p, unsigned target) {
  flag_poll(p, target);
}
__device__ __forceinline__ void flag_signal(unsigned* p, int n, int lane) {
  if (lane == 0) asm volatile("fence.release.gpu;" ::: "memory");
  __syncwarp();
  if (lane < n) asm volatile("red.relaxed.gpu.global.add.u32 [%0], 1;" ::"l"(p + 32 * lane) : "memory");
}
__device__ __forceinline__ void flag_bump(unsigned* p) {
  asm volatile("red.relaxed.gpu.global.add.u32 [%0], 1;" ::"l"(p) : "memory");
}
__device__ __forceinline__ void fence_async_smem() { asm volatile("fence.proxy.async.shared::cta;" ::: "memory"); }
__device__ __forceinline__ void wg_sync(int id) { asm volatile("bar.sync %0, 128;" ::"r"(id) : "memory"); }

__device__ __forceinline__ void tma_2d(uint32_t dst, const CUtensorMap* tm, int c0, int c1, uint32_t bar) {
  asm volatile("cp.async.bulk.tensor.2d.shared::cluster.global.mbarrier::complete_tx::bytes [%0], [%1, {%3, %4}], [%2];"
               ::"r"(dst), "l"(tm), "r"(bar), "r"(c0), "r"(c1) : "memory");
}
__device__ __forceinline__ void tma_3d(uint32_t dst, const CUtensorMap* tm, int c0, int c1, int c2, uint32_t bar) {
  asm volatile("cp.async.bulk.tensor.3d.shared::cluster.global.mbarrier::complete_tx::bytes [%0], [%1, {%3, %4, %5}], [%2];"
               ::"r"(dst), "l"(tm), "r"(bar), "r"(c0), "r"(c1), "r"(c2) : "memory");
}
__device__ __forceinline__ void bulk_load(uint32_t dst, const void* src, uint32_t bytes, uint32_t bar) {
  asm volatile("cp.async.bulk.shared::cluster.global.mbarrier::complete_tx::bytes [%0], [%1], %2, [%3];"
               ::"r"(dst), "l"(src), "r"(bytes), "r"(bar) : "memory");
}
__device__ __forceinline__ void bulk_store(void* dst, uint32_t src, uint32_t bytes) {
  asm volatile("cp.async.bulk.global.shared::cta.bulk_group [%0], [%1], %2;" ::"l"(dst), "r"(src), "r"(bytes) : "memory");
}
__device__ __forceinline__ void bulk_wait_read() {
  asm volatile("cp.async.bulk.commit_group;\ncp.async.bulk.wait_group.read 0;" ::: "memory");
}

__device__ __forceinline__ void publish(void* dst, uint32_t src, uint32_t bytes) {
  bulk_store(dst, src, bytes);
  bulk_wait_read();
}

__device__ __forceinline__ void wg_fence() { asm volatile("wgmma.fence.sync.aligned;" ::: "memory"); }
__device__ __forceinline__ void wg_commit() { asm volatile("wgmma.commit_group.sync.aligned;" ::: "memory"); }
template <int N> __device__ __forceinline__ void wg_wait() { asm volatile("wgmma.wait_group.sync.aligned %0;" ::"n"(N) : "memory"); }
__device__ __forceinline__ uint32_t desc_lo(uint32_t addr, uint32_t lbo) { return ((addr & 0x3FFFF) >> 4) | ((lbo >> 4) << 16); }
constexpr uint32_t desc_hi(uint32_t sbo, uint32_t swz) { return (sbo >> 4) | (swz << 30); }
constexpr uint32_t HI_SW128 = desc_hi(1024, 1), HI_SW64 = desc_hi(512, 2), HI_SW32 = desc_hi(256, 3), HI_NONE = desc_hi(128, 0);
template <int N> __device__ __forceinline__ void pin(float* d) {
#pragma unroll
  for (int i = 0; i < N; i++) asm volatile("" : "+f"(d[i])::"memory");
}

__device__ __forceinline__ uint32_t lds32(uint32_t a) {
  uint32_t v;
  asm volatile("ld.volatile.shared.u32 %0, [%1];" : "=r"(v) : "r"(a) : "memory");
  return v;
}
__device__ __forceinline__ uint2 ldg64(const void* a) {
  uint2 v;
  asm volatile("ld.global.nc.v2.u32 {%0, %1}, [%2];" : "=r"(v.x), "=r"(v.y) : "l"(a) : "memory");
  return v;
}
__device__ __forceinline__ void ldsm4(uint32_t* r, uint32_t a) {
  asm volatile("ldmatrix.sync.aligned.m8n8.x4.shared.b16 {%0, %1, %2, %3}, [%4];"
               : "=r"(r[0]), "=r"(r[1]), "=r"(r[2]), "=r"(r[3]) : "r"(a) : "memory");
}
__device__ __forceinline__ void ldsm4t(uint32_t* r, uint32_t a) {
  asm volatile("ldmatrix.sync.aligned.m8n8.x4.trans.shared.b16 {%0, %1, %2, %3}, [%4];"
               : "=r"(r[0]), "=r"(r[1]), "=r"(r[2]), "=r"(r[3]) : "r"(a) : "memory");
}
__device__ __forceinline__ uint2 lds64(uint32_t a) {
  uint2 v;
  asm volatile("ld.shared.v2.u32 {%0, %1}, [%2];" : "=r"(v.x), "=r"(v.y) : "r"(a) : "memory");
  return v;
}
__device__ __forceinline__ uint4 lds128(uint32_t a) {
  uint4 v;
  asm volatile("ld.shared.v4.u32 {%0, %1, %2, %3}, [%4];" : "=r"(v.x), "=r"(v.y), "=r"(v.z), "=r"(v.w) : "r"(a) : "memory");
  return v;
}
__device__ __forceinline__ void sts128(uint32_t a, uint32_t x, uint32_t y, uint32_t z, uint32_t w) {
  asm volatile("st.shared.v4.u32 [%0], {%1, %2, %3, %4};" ::"r"(a), "r"(x), "r"(y), "r"(z), "r"(w) : "memory");
}
__device__ __forceinline__ void stsm4(uint32_t a, const uint32_t* r) {
  asm volatile("stmatrix.sync.aligned.m8n8.x4.shared.b16 [%0], {%1, %2, %3, %4};" ::"r"(a), "r"(r[0]), "r"(r[1]), "r"(r[2]), "r"(r[3]) : "memory");
}
__device__ __forceinline__ uint32_t pack2(float lo, float hi) {
  uint32_t r;
  asm("cvt.rn.bf16x2.f32 %0, %1, %2;" : "=r"(r) : "f"(hi), "f"(lo));
  return r;
}
__device__ __forceinline__ uint32_t movm(uint32_t a) {
  uint32_t d;
  asm volatile("movmatrix.sync.aligned.m8n8.trans.b16 %0, %1;" : "=r"(d) : "r"(a));
  return d;
}
__device__ __forceinline__ uint32_t bmul(uint32_t a, uint32_t b) {
  uint32_t d;
  asm("mul.rn.bf16x2 %0, %1, %2;" : "=r"(d) : "r"(a), "r"(b));
  return d;
}
__device__ __forceinline__ uint32_t badd(uint32_t a, uint32_t b) {
  uint32_t d;
  asm("add.rn.bf16x2 %0, %1, %2;" : "=r"(d) : "r"(a), "r"(b));
  return d;
}
__device__ __forceinline__ uint32_t bfma(uint32_t a, uint32_t b, uint32_t c) {
  uint32_t d;
  asm("fma.rn.bf16x2 %0, %1, %2, %3;" : "=r"(d) : "r"(a), "r"(b), "r"(c));
  return d;
}
__device__ __forceinline__ float bf_lo(uint32_t x) { return __uint_as_float(x << 16); }
__device__ __forceinline__ float bf_hi(uint32_t x) { return __uint_as_float(x & 0xFFFF0000u); }
__device__ __forceinline__ float ex2(float x) {
  float y;
  asm("ex2.approx.ftz.f32 %0, %1;" : "=f"(y) : "f"(x));
  return y;
}
__device__ __forceinline__ float rcp(float x) {
  float y;
  asm("rcp.approx.ftz.f32 %0, %1;" : "=f"(y) : "f"(x));
  return y;
}
__device__ __forceinline__ void mma16816(float* d, uint32_t a0, uint32_t a1, uint32_t a2, uint32_t a3, uint32_t b0, uint32_t b1) {
  asm volatile("mma.sync.aligned.m16n8k16.row.col.f32.bf16.bf16.f32 {%0, %1, %2, %3}, {%4, %5, %6, %7}, {%8, %9}, {%0, %1, %2, %3};"
               : "+f"(d[0]), "+f"(d[1]), "+f"(d[2]), "+f"(d[3])
               : "r"(a0), "r"(a1), "r"(a2), "r"(a3), "r"(b0), "r"(b1));
}
__device__ __forceinline__ void mma1688(float* d, uint32_t a0, uint32_t a1, uint32_t b0) {
  asm volatile("mma.sync.aligned.m16n8k8.row.col.f32.bf16.bf16.f32 {%0, %1, %2, %3}, {%4, %5}, {%6}, {%0, %1, %2, %3};"
               : "+f"(d[0]), "+f"(d[1]), "+f"(d[2]), "+f"(d[3])
               : "r"(a0), "r"(a1), "r"(b0));
}

template <int N> struct WgRS;
template <int N> struct WgSST;
template <> struct WgRS<32> {
  template <uint32_t HB>
  static __device__ __forceinline__ void mma(float* d, const uint32_t* a, uint32_t db) {
    asm volatile("{\n.reg .pred p;\n.reg .b64 db;\nsetp.ne.b32 p, %22, 0;\n"
      "mov.b64 db, {%20, %21};\n"
      "wgmma.mma_async.sync.aligned.m64n32k16.f32.bf16.bf16 {"
      "%0, %1, %2, %3, %4, %5, %6, %7, %8, %9, %10, %11, %12, %13, %14, %15"
      "}, {%16, %17, %18, %19}, db, p, 1, 1, 1;\n}\n"
      : "+f"(d[0]), "+f"(d[1]), "+f"(d[2]), "+f"(d[3]), "+f"(d[4]), "+f"(d[5]), "+f"(d[6]), "+f"(d[7]),
        "+f"(d[8]), "+f"(d[9]), "+f"(d[10]), "+f"(d[11]), "+f"(d[12]), "+f"(d[13]), "+f"(d[14]), "+f"(d[15])
      : "r"(a[0]), "r"(a[1]), "r"(a[2]), "r"(a[3]), "r"(db), "n"(HB), "n"(1));
  }
  template <uint32_t HB>
  static __device__ __forceinline__ void set(float* d, const uint32_t* a, uint32_t db) {
    asm volatile("{\n.reg .pred p;\n.reg .b64 db;\nsetp.ne.b32 p, %22, 0;\n"
      "mov.b64 db, {%20, %21};\n"
      "wgmma.mma_async.sync.aligned.m64n32k16.f32.bf16.bf16 {"
      "%0, %1, %2, %3, %4, %5, %6, %7, %8, %9, %10, %11, %12, %13, %14, %15"
      "}, {%16, %17, %18, %19}, db, p, 1, 1, 1;\n}\n"
      : "=f"(d[0]), "=f"(d[1]), "=f"(d[2]), "=f"(d[3]), "=f"(d[4]), "=f"(d[5]), "=f"(d[6]), "=f"(d[7]),
        "=f"(d[8]), "=f"(d[9]), "=f"(d[10]), "=f"(d[11]), "=f"(d[12]), "=f"(d[13]), "=f"(d[14]), "=f"(d[15])
      : "r"(a[0]), "r"(a[1]), "r"(a[2]), "r"(a[3]), "r"(db), "n"(HB), "n"(0));
  }
};
template <> struct WgRS<64> {
  template <uint32_t HB>
  static __device__ __forceinline__ void mma(float* d, const uint32_t* a, uint32_t db) {
    asm volatile("{\n.reg .pred p;\n.reg .b64 db;\nsetp.ne.b32 p, %38, 0;\n"
      "mov.b64 db, {%36, %37};\n"
      "wgmma.mma_async.sync.aligned.m64n64k16.f32.bf16.bf16 {"
      "%0, %1, %2, %3, %4, %5, %6, %7, %8, %9, %10, %11, %12, %13, %14, %15, "
      "%16, %17, %18, %19, %20, %21, %22, %23, %24, %25, %26, %27, %28, %29, %30, %31"
      "}, {%32, %33, %34, %35}, db, p, 1, 1, 1;\n}\n"
      : "+f"(d[0]), "+f"(d[1]), "+f"(d[2]), "+f"(d[3]), "+f"(d[4]), "+f"(d[5]), "+f"(d[6]), "+f"(d[7]),
        "+f"(d[8]), "+f"(d[9]), "+f"(d[10]), "+f"(d[11]), "+f"(d[12]), "+f"(d[13]), "+f"(d[14]), "+f"(d[15]),
        "+f"(d[16]), "+f"(d[17]), "+f"(d[18]), "+f"(d[19]), "+f"(d[20]), "+f"(d[21]), "+f"(d[22]), "+f"(d[23]),
        "+f"(d[24]), "+f"(d[25]), "+f"(d[26]), "+f"(d[27]), "+f"(d[28]), "+f"(d[29]), "+f"(d[30]), "+f"(d[31])
      : "r"(a[0]), "r"(a[1]), "r"(a[2]), "r"(a[3]), "r"(db), "n"(HB), "n"(1));
  }
  template <uint32_t HB>
  static __device__ __forceinline__ void set(float* d, const uint32_t* a, uint32_t db) {
    asm volatile("{\n.reg .pred p;\n.reg .b64 db;\nsetp.ne.b32 p, %38, 0;\n"
      "mov.b64 db, {%36, %37};\n"
      "wgmma.mma_async.sync.aligned.m64n64k16.f32.bf16.bf16 {"
      "%0, %1, %2, %3, %4, %5, %6, %7, %8, %9, %10, %11, %12, %13, %14, %15, "
      "%16, %17, %18, %19, %20, %21, %22, %23, %24, %25, %26, %27, %28, %29, %30, %31"
      "}, {%32, %33, %34, %35}, db, p, 1, 1, 1;\n}\n"
      : "=f"(d[0]), "=f"(d[1]), "=f"(d[2]), "=f"(d[3]), "=f"(d[4]), "=f"(d[5]), "=f"(d[6]), "=f"(d[7]),
        "=f"(d[8]), "=f"(d[9]), "=f"(d[10]), "=f"(d[11]), "=f"(d[12]), "=f"(d[13]), "=f"(d[14]), "=f"(d[15]),
        "=f"(d[16]), "=f"(d[17]), "=f"(d[18]), "=f"(d[19]), "=f"(d[20]), "=f"(d[21]), "=f"(d[22]), "=f"(d[23]),
        "=f"(d[24]), "=f"(d[25]), "=f"(d[26]), "=f"(d[27]), "=f"(d[28]), "=f"(d[29]), "=f"(d[30]), "=f"(d[31])
      : "r"(a[0]), "r"(a[1]), "r"(a[2]), "r"(a[3]), "r"(db), "n"(HB), "n"(0));
  }
};
template <> struct WgSST<48> {
  template <uint32_t HA, uint32_t HB>
  static __device__ __forceinline__ void mma(float* d, uint32_t da, uint32_t db, int sc) {
    asm volatile("{\n.reg .pred p;\n.reg .b64 da, db;\nsetp.ne.b32 p, %28, 0;\n"
      "mov.b64 da, {%24, %25};\nmov.b64 db, {%26, %27};\n"
      "wgmma.mma_async.sync.aligned.m64n48k16.f32.bf16.bf16 {"
      "%0, %1, %2, %3, %4, %5, %6, %7, %8, %9, %10, %11, %12, %13, %14, %15, "
      "%16, %17, %18, %19, %20, %21, %22, %23"
      "}, da, db, p, 1, 1, 0, 1;\n}\n"
      : "+f"(d[0]), "+f"(d[1]), "+f"(d[2]), "+f"(d[3]), "+f"(d[4]), "+f"(d[5]), "+f"(d[6]), "+f"(d[7]),
        "+f"(d[8]), "+f"(d[9]), "+f"(d[10]), "+f"(d[11]), "+f"(d[12]), "+f"(d[13]), "+f"(d[14]), "+f"(d[15]),
        "+f"(d[16]), "+f"(d[17]), "+f"(d[18]), "+f"(d[19]), "+f"(d[20]), "+f"(d[21]), "+f"(d[22]), "+f"(d[23])
      : "r"(da), "n"(HA), "r"(db), "n"(HB), "r"(sc));
  }
};
template <> struct WgSST<80> {
  template <uint32_t HA, uint32_t HB>
  static __device__ __forceinline__ void mma(float* d, uint32_t da, uint32_t db, int sc) {
    asm volatile("{\n.reg .pred p;\n.reg .b64 da, db;\nsetp.ne.b32 p, %44, 0;\n"
      "mov.b64 da, {%40, %41};\nmov.b64 db, {%42, %43};\n"
      "wgmma.mma_async.sync.aligned.m64n80k16.f32.bf16.bf16 {"
      "%0, %1, %2, %3, %4, %5, %6, %7, %8, %9, %10, %11, %12, %13, %14, %15, "
      "%16, %17, %18, %19, %20, %21, %22, %23, %24, %25, %26, %27, %28, %29, %30, %31, "
      "%32, %33, %34, %35, %36, %37, %38, %39"
      "}, da, db, p, 1, 1, 0, 1;\n}\n"
      : "+f"(d[0]), "+f"(d[1]), "+f"(d[2]), "+f"(d[3]), "+f"(d[4]), "+f"(d[5]), "+f"(d[6]), "+f"(d[7]),
        "+f"(d[8]), "+f"(d[9]), "+f"(d[10]), "+f"(d[11]), "+f"(d[12]), "+f"(d[13]), "+f"(d[14]), "+f"(d[15]),
        "+f"(d[16]), "+f"(d[17]), "+f"(d[18]), "+f"(d[19]), "+f"(d[20]), "+f"(d[21]), "+f"(d[22]), "+f"(d[23]),
        "+f"(d[24]), "+f"(d[25]), "+f"(d[26]), "+f"(d[27]), "+f"(d[28]), "+f"(d[29]), "+f"(d[30]), "+f"(d[31]),
        "+f"(d[32]), "+f"(d[33]), "+f"(d[34]), "+f"(d[35]), "+f"(d[36]), "+f"(d[37]), "+f"(d[38]), "+f"(d[39])
      : "r"(da), "n"(HA), "r"(db), "n"(HB), "r"(sc));
  }
};
template <> struct WgSST<192> {
  template <uint32_t HA, uint32_t HB>
  static __device__ __forceinline__ void mma(float* d, uint32_t da, uint32_t db, int sc) {
    asm volatile("{\n.reg .pred p;\n.reg .b64 da, db;\nsetp.ne.b32 p, %100, 0;\n"
      "mov.b64 da, {%96, %97};\nmov.b64 db, {%98, %99};\n"
      "wgmma.mma_async.sync.aligned.m64n192k16.f32.bf16.bf16 {"
      "%0, %1, %2, %3, %4, %5, %6, %7, %8, %9, %10, %11, %12, %13, %14, %15, "
      "%16, %17, %18, %19, %20, %21, %22, %23, %24, %25, %26, %27, %28, %29, %30, %31, "
      "%32, %33, %34, %35, %36, %37, %38, %39, %40, %41, %42, %43, %44, %45, %46, %47, "
      "%48, %49, %50, %51, %52, %53, %54, %55, %56, %57, %58, %59, %60, %61, %62, %63, "
      "%64, %65, %66, %67, %68, %69, %70, %71, %72, %73, %74, %75, %76, %77, %78, %79, "
      "%80, %81, %82, %83, %84, %85, %86, %87, %88, %89, %90, %91, %92, %93, %94, %95"
      "}, da, db, p, 1, 1, 0, 1;\n}\n"
      : "+f"(d[0]), "+f"(d[1]), "+f"(d[2]), "+f"(d[3]), "+f"(d[4]), "+f"(d[5]), "+f"(d[6]), "+f"(d[7]),
        "+f"(d[8]), "+f"(d[9]), "+f"(d[10]), "+f"(d[11]), "+f"(d[12]), "+f"(d[13]), "+f"(d[14]), "+f"(d[15]),
        "+f"(d[16]), "+f"(d[17]), "+f"(d[18]), "+f"(d[19]), "+f"(d[20]), "+f"(d[21]), "+f"(d[22]), "+f"(d[23]),
        "+f"(d[24]), "+f"(d[25]), "+f"(d[26]), "+f"(d[27]), "+f"(d[28]), "+f"(d[29]), "+f"(d[30]), "+f"(d[31]),
        "+f"(d[32]), "+f"(d[33]), "+f"(d[34]), "+f"(d[35]), "+f"(d[36]), "+f"(d[37]), "+f"(d[38]), "+f"(d[39]),
        "+f"(d[40]), "+f"(d[41]), "+f"(d[42]), "+f"(d[43]), "+f"(d[44]), "+f"(d[45]), "+f"(d[46]), "+f"(d[47]),
        "+f"(d[48]), "+f"(d[49]), "+f"(d[50]), "+f"(d[51]), "+f"(d[52]), "+f"(d[53]), "+f"(d[54]), "+f"(d[55]),
        "+f"(d[56]), "+f"(d[57]), "+f"(d[58]), "+f"(d[59]), "+f"(d[60]), "+f"(d[61]), "+f"(d[62]), "+f"(d[63]),
        "+f"(d[64]), "+f"(d[65]), "+f"(d[66]), "+f"(d[67]), "+f"(d[68]), "+f"(d[69]), "+f"(d[70]), "+f"(d[71]),
        "+f"(d[72]), "+f"(d[73]), "+f"(d[74]), "+f"(d[75]), "+f"(d[76]), "+f"(d[77]), "+f"(d[78]), "+f"(d[79]),
        "+f"(d[80]), "+f"(d[81]), "+f"(d[82]), "+f"(d[83]), "+f"(d[84]), "+f"(d[85]), "+f"(d[86]), "+f"(d[87]),
        "+f"(d[88]), "+f"(d[89]), "+f"(d[90]), "+f"(d[91]), "+f"(d[92]), "+f"(d[93]), "+f"(d[94]), "+f"(d[95])
      : "r"(da), "n"(HA), "r"(db), "n"(HB), "r"(sc));
  }
};

struct FftConst {
  uint32_t f[2][4], fi[4][4];
  uint32_t ta[2][2], tb[2][2];
};
__device__ __forceinline__ void cis(int m, float scale, float& c, float& s) {
  const float a = (float)m * (-6.283185307179586f * scale);
  c = __cosf(a);
  s = __sinf(a);
}
__device__ __forceinline__ void fft_tables(uint32_t (&v)[12], int tw) {
  const int row = tw >> 2, ch = tw & 3;
#pragma unroll
  for (int i = 0; i < 4; i++) {
    float c[2], s[2], x[2];
#pragma unroll
    for (int e = 0; e < 2; e++) {
      cis((((32 * (8 * ch + 2 * i + e) + 15) * (4 * row - 63) + 2048) & 4095) - 2048, 1.f / 4096, c[e], s[e]);
      float gc, gs;
      cis((((row & 15) * (8 * (ch & 1) + 2 * i + e) + 8) & 15) - 8, 1.f / 16, gc, gs);
      x[e] = (row >> 4) == (ch >> 1) ? gc : (ch >> 1) ? gs : -gs;
    }
    v[i] = pack2(c[0] * 0.125f, c[1] * 0.125f);
    v[4 + i] = pack2(s[0] * 0.125f, s[1] * 0.125f);
    v[8 + i] = pack2(x[0], x[1]);
  }
#pragma unroll
  for (int i = 0; i < 12; i++) asm volatile("" : "+r"(v[i]));
}
__device__ __forceinline__ void fft_tables_store(const uint32_t (&v)[12], uint32_t sb, int tw) {
  const int row = tw >> 2;
  const uint32_t x = ((tw ^ (row >> 1)) & 3) << 4, a = sb + OFF_FT + (16 * (row >> 3) + (row & 7)) * 64 + x;
  sts128(a, v[0], v[1], v[2], v[3]);
  sts128(a + 512, v[4], v[5], v[6], v[7]);
  sts128(sb + OFF_GT + row * 64 + x, v[8], v[9], v[10], v[11]);
}
__device__ __forceinline__ void fft_twiddles(uint32_t (&v)[2], int tw) {
  float a[2], s[2];
#pragma unroll
  for (int i = 0; i < 2; i++) {
    float c;
    cis((2 * (2 * (tw & 3) + i) - 15) * (4 * (tw >> 2) - 63), 1.f / 4096, c, s[i]);
    a[i] = __fdividef(-s[i], 1.f + c);
  }
  v[0] = pack2(a[0], a[1]);
  v[1] = pack2(s[0], s[1]);
  asm volatile("" : "+r"(v[0]), "+r"(v[1]));
}
__device__ __forceinline__ void fft_matrices(FftConst& k, uint32_t sb, int w, int lane) {
  const uint32_t x = (lane >> 1) & 3;
  const uint2 t0 = lds64(sb + OFF_TT + 256 * w + 8 * lane), t1 = lds64(sb + OFF_TT + 256 * w + 8 * (lane ^ 3));
  k.ta[0][0] = t0.x;
  k.tb[0][0] = t0.y;
  k.ta[1][1] = __byte_perm(t1.x, 0, 0x1032);
  k.tb[1][1] = __byte_perm(t1.y, 0, 0x1032);
#pragma unroll
  for (int j = 0; j < 2; j++) {
    k.ta[1 - j][j] = k.ta[j][j] ^ 0x80008000u;
    k.tb[1 - j][j] = k.tb[j][j] ^ 0x80008000u;
    asm volatile("" : "+r"(k.ta[0][j]), "+r"(k.tb[0][j]), "+r"(k.ta[1][j]), "+r"(k.tb[1][j]));
  }
#pragma unroll
  for (int i = 0; i < 2; i++) {
    ldsm4(k.f[i], sb + OFF_FT + (16 * w + (lane & 15)) * 64 + (((2 * i + (lane >> 4)) ^ x) << 4));
    ldsm4t(k.fi[i], sb + OFF_FT + (32 * i + lane) * 64 + ((w ^ x) << 4));
#pragma unroll
    for (int j = 0; j < 4; j++) {
      k.fi[2 + i][j] = (j & 1) ? k.fi[i][j - 1] ^ 0x80008000u : k.fi[i][j + 1];
      asm volatile("" : "+r"(k.fi[2 + i][j]));
    }
  }
}
__device__ __forceinline__ void rot(uint32_t& x, uint32_t& y, uint32_t a, uint32_t b) {
  x = bfma(a, y, x);
  y = bfma(b, x, y);
  x = bfma(a, y, x);
}
__device__ __forceinline__ void twiddle_fwd(uint32_t (&a)[4][4], float* d, const FftConst& k) {
#pragma unroll
  for (int q = 0; q < 4; q++)
#pragma unroll
    for (int j = 0; j < 2; j++) {
      const float* x = d + 8 * q + 4 * j;
      uint32_t re = pack2(x[0], x[1]), im = pack2(x[2], x[3]);
      rot(re, im, k.ta[0][j], k.tb[0][j]);
      a[q & 2][2 * j + (q & 1)] = re;
      a[(q & 2) + 1][2 * j + (q & 1)] = im;
    }
}
__device__ __forceinline__ void g_step(float* d, const uint32_t (&a)[4][4], uint32_t dre, uint32_t dim) {
  WgRS<32>::set<HI_SW64>(d, a[0], dre);
  WgRS<32>::set<HI_SW64>(d + 16, a[2], dre);
  WgRS<32>::mma<HI_SW64>(d, a[1], dim);
  WgRS<32>::mma<HI_SW64>(d + 16, a[3], dim);
  wg_commit();
}

__device__ __forceinline__ void products(uint32_t (&a)[4][4], const float* H, const float* U, int p) {
#pragma unroll
  for (int j = 0; j < 2; j++)
#pragma unroll
    for (int m = 2 * p; m < 2 * p + 2; m++) {
      float pr[2], pi[2];
#pragma unroll
      for (int x = 0; x < 2; x++)
#pragma unroll
        for (int q = 0; q <= m; q++) {
          const int ih = 16 * (q >> 1) + 2 * (q & 1) + 4 * j + x, iu = 16 * ((m - q) >> 1) + 2 * ((m - q) & 1) + 4 * j + x;
          pr[x] = q ? fmaf(H[ih], U[iu], pr[x]) : H[ih] * U[iu];
          pi[x] = q ? fmaf(H[ih], U[iu + 8], pi[x]) : H[ih] * U[iu + 8];
          pr[x] = fmaf(-H[ih + 8], U[iu + 8], pr[x]);
          pi[x] = fmaf(H[ih + 8], U[iu], pi[x]);
        }
      a[m & 2][2 * j + (m & 1)] = pack2(pr[0], pr[1]);
      a[(m & 2) + 1][2 * j + (m & 1)] = pack2(pi[0], pi[1]);
    }
}

__device__ __forceinline__ void conv_channel(const FftConst& k, uint32_t sb, int c, int wg, int w, int lane) {
  const uint32_t cb = sb + off_ch(c), bars = sb + OFF_BAR;
  const uint32_t du = desc_lo(cb, 1024), dg = desc_lo(sb + OFF_GT, 16), dz = desc_lo(cb + U_BYTES, 16);
  float U[32], H[32];
  uint32_t a[4][4], e[4][4];
  const float dv = __uint_as_float(lds32(sb + OFF_D + 4 * c));
  wg_fence();
  WgRS<64>::set<HI_SW32>(H, k.f[0], du + 256);
  WgRS<64>::mma<HI_SW32>(H, k.f[1], du + 256 + 32);
  wg_commit();
  wg_wait<0>();
  pin<32>(H);
  twiddle_fwd(a, H, k);
  mbar_wait(bars + 8 * (B_U + (c < 3 ? c : 3)), 0);
  TSM(w == 0 && c < 3, 7 + wg);
  wg_fence();
  WgRS<64>::set<HI_SW32>(U, k.f[0], du);
  WgRS<64>::mma<HI_SW32>(U, k.f[1], du + 32);
  wg_commit();
  g_step(H, a, dg, dg + 64);
  wg_wait<1>();
  pin<32>(U);
  twiddle_fwd(e, U, k);
  wg_fence();
  g_step(U, e, dg, dg + 64);
  wg_wait<0>();
  pin<32>(U);
  pin<32>(H);
#pragma unroll
  for (int j = 0; j < 4; j++) H[4 * (j >> 1) + (j & 1)] += dv;
  float V[32];
#pragma unroll
  for (int p = 0; p < 2; p++) {
    products(a, H, U, p);
    wg_fence();
    WgRS<32>::set<HI_SW64>(V + 16 * p, a[2 * p], dg + 64);
    WgRS<32>::mma<HI_SW64>(V + 16 * p, a[2 * p + 1], dg);
    wg_commit();
  }
  const uint32_t za = cb + U_BYTES + (8 * w + (lane & 7)) * 128 + (((lane >> 3) ^ (lane & 7)) << 4);
  const uint32_t ya = cb + (lane >> 4) * 1024 + (8 * w + (lane & 7)) * 32 + ((((lane >> 3) ^ (lane >> 2)) & 1) << 4);
  wg_sync(1 + wg);
#pragma unroll
  for (int p = 0; p < 2; p++) {
    if (p == 0) wg_wait<1>();
    else wg_wait<0>();
    pin<16>(V + 16 * p);
#pragma unroll
    for (int i = 0; i < 4; i++) {
      const int j = i & 1;
      const float* x = V + 16 * p + 4 * j + (i & 2);
      e[p][i] = pack2(x[8], x[9]);
      e[2 + p][i] = pack2(x[0], x[1]);
      rot(e[p][i], e[2 + p][i], k.ta[1][j], k.tb[1][j]);
    }
    stsm4(za ^ (64 * p), e[p]);
    stsm4((za ^ (64 * p)) + 4096, e[2 + p]);
  }
  fence_async_smem();
  wg_sync(1 + wg);
  wg_fence();
  WgRS<64>::set<HI_SW128>(H, k.fi[0], dz);
#pragma unroll
  for (int ks = 1; ks < 4; ks++) WgRS<64>::mma<HI_SW128>(H, k.fi[ks], dz + 128 * ks);
  wg_commit();
  wg_wait<0>();
  pin<32>(H);
  if (lane == 0) mbar_arrive(bars + 8 * B_CVD);
  TSIF(w == 0, 88 + c);
#pragma unroll
  for (int j = 0; j < 8; j++)
    a[j >> 2][j & 3] = j < 2 ? pack2(H[4 * j], H[4 * j + 1]) : pack2(H[4 * j] + H[4 * j - 6], H[4 * j + 1] + H[4 * j - 5]);
  stsm4(ya, a[0]);
  stsm4(ya + 2048, a[1]);
  fence_async_smem();
  __syncwarp();
}

__device__ __forceinline__ void prep_slab(uint4* res, const uint2* sw, uint32_t sb, int slab, int w, int lane) {
  const int t = lane & 3, tp = (lane & 7) >> 1, pos = 8 * tp + 2 * (((lane >> 3) + tp) & 3) + (lane & 1);
  const uint32_t base = sb + OFF_KVS + slab * KVS_BYTES + pos * 128;
  uint32_t kk[2][4][4], vv[2][4];
  mbar_wait(sb + OFF_BAR + 8 * (B_KV + slab), 0);
#pragma unroll
  for (int h = 0; h < 2; h++) {
#pragma unroll
    for (int j = 0; j < 4; j++) {
      const uint32_t a = base + 128 * j;
      ldsm4t(kk[h][j], a + (((w + 4 * h) ^ ((a >> 7) & 7)) << 4));
    }
    const uint32_t a = base + KVS_V;
    ldsm4t(vv[h], a + (((w + 4 * h) ^ ((a >> 7) & 7)) << 4));
  }
#pragma unroll
  for (int h = 0; h < 2; h++) {
    uint32_t (&k)[4][4] = kk[h];
    uint32_t (&v)[4] = vv[h];
    const uint32_t w0 = __byte_perm(sw[h].x, 0, 0x1010), w1 = __byte_perm(sw[h].x, 0, 0x3232);
    const uint32_t w2 = __byte_perm(sw[h].y, 0, 0x1010), w3 = __byte_perm(sw[h].y, 0, 0x3232);
#pragma unroll
    for (int m = 0; m < 4; m++)
      v[m] = bmul(badd(badd(badd(bmul(k[0][m], w3), bmul(k[1][m], w2)), bmul(k[2][m], w1)), bmul(k[3][m], w0)), v[m]);
    uint32_t a[4];
#pragma unroll
    for (int m = 0; m < 4; m++) a[m] = (t & 1) ? v[(m + 3) & 3] : v[m];
    res[h] = (t & 2) ? make_uint4(a[2], a[3], a[0], a[1]) : make_uint4(a[0], a[1], a[2], a[3]);
  }
}

__device__ __forceinline__ void prep_gate(const Params& p, uint32_t sb, int b, int w, int lane) {
  uint2 gw[5], x[4][5];
#pragma unroll
  for (int j = 0; j < 5; j++) gw[j] = ldg64(reinterpret_cast<const uint2*>(p.gate_w) + lane + 32 * j);
#pragma unroll
  for (int i = 0; i < 4; i++)
#pragma unroll
    for (int j = 0; j < 5; j++)
      x[i][j] = ldg64(reinterpret_cast<const uint2*>(p.q) + (16 * b + 4 * w + i) * (DIM / 4) + lane + 32 * j);
  float s[4];
#pragma unroll
  for (int i = 0; i < 4; i++) {
    s[i] = 0.f;
#pragma unroll
    for (int j = 0; j < 5; j++) {
      const uint32_t m0 = bmul(x[i][j].x, gw[j].x), m1 = bmul(x[i][j].y, gw[j].y);
      s[i] += (bf_lo(m0) + bf_hi(m0)) + (bf_lo(m1) + bf_hi(m1));
    }
  }
  const bool h = lane & 16, q = lane & 8;
  const float a = (h ? s[2] : s[0]) + __shfl_xor_sync(0xffffffffu, h ? s[0] : s[2], 16);
  const float c = (h ? s[3] : s[1]) + __shfl_xor_sync(0xffffffffu, h ? s[1] : s[3], 16);
  float z = (q ? c : a) + __shfl_xor_sync(0xffffffffu, q ? a : c, 8);
#pragma unroll
  for (int o = 4; o > 0; o >>= 1) z += __shfl_xor_sync(0xffffffffu, z, o);
  z = bf_lo(pack2(z, 0.f));
  z = bf_lo(pack2(__fdividef(1.f, 1.f + __expf(-z)), 0.f));
  mbar_wait(sb + OFF_BAR + 8 * B_S3, 0);
  if ((lane & 7) == 0) asm volatile("st.shared.f32 [%0], %1;" ::"r"(sb + OFF_GATE + 64 * (b & 7) + 16 * w + (lane >> 1)), "f"(z) : "memory");
  fence_async_smem();
}

__device__ __forceinline__ uint32_t bmax(uint32_t a, uint32_t b) {
  uint32_t d;
  asm("max.bf16x2 %0, %1, %2;" : "=r"(d) : "r"(a), "r"(b));
  return d;
}
__device__ __forceinline__ void softmax_two(const float (&l)[2][2], uint32_t& p0, uint32_t& p1) {
  constexpr float kScale = 0.22360679774997896f, kLog2e = 1.4426950408889634f;
  const uint32_t r0 = pack2(l[0][0], l[1][0]), r1 = pack2(l[0][1], l[1][1]);
  const uint32_t x0 = pack2(bf_lo(r0) * kScale, bf_hi(r0) * kScale), x1 = pack2(bf_lo(r1) * kScale, bf_hi(r1) * kScale);
  uint32_t m = bmax(x0, x1);
  m = bmax(m, __shfl_xor_sync(0xffffffffu, m, 1));
  m = bmax(m, __shfl_xor_sync(0xffffffffu, m, 2));
  const float m0 = bf_lo(m) * kLog2e, m1 = bf_hi(m) * kLog2e;
  p0 = pack2(ex2(bf_lo(x0) * kLog2e - m0), ex2(bf_lo(x1) * kLog2e - m0));
  p1 = pack2(ex2(bf_hi(x0) * kLog2e - m1), ex2(bf_hi(x1) * kLog2e - m1));
}

__device__ __forceinline__ void halo_read(uint32_t (&kpv)[10], uint32_t (&vpv)[10], uint32_t (&tg)[7], const uint4* hp) {
#pragma unroll
  for (int j = 0; j < 7; j++) {
    uint32_t x0, x1, x2;
    asm volatile("ld.relaxed.gpu.global.v4.u32 {%0, %1, %2, %3}, [%4];"
                 : "=r"(x0), "=r"(x1), "=r"(x2), "=r"(tg[j]) : "l"(hp + 32 * j) : "memory");
    if (j < 4) kpv[3 * j] = x0; else vpv[3 * j - 10] = x0;
    if (j < 3) kpv[3 * j + 1] = x1; else vpv[3 * j - 9] = x1;
    if (j < 3) kpv[3 * j + 2] = x2; else if (j < 6) vpv[3 * j - 8] = x2;
  }
}

template <int ROT>
__device__ __forceinline__ void pack_qkv(const float* acc, uint32_t (&qlo)[10], uint32_t (&qhi)[10], uint32_t (&klo)[10],
                                         uint32_t (&khi)[10], uint32_t (&vlo)[10], uint32_t (&vhi)[10]) {
#pragma unroll
  for (int j = 0; j < 10; j++) {
    const int x = (j + ROT) % 10, tq = x < 8 ? x : 16 + x, tk = x < 8 ? 8 + x : 18 + x, tv = x < 8 ? 16 + x : 20 + x;
    khi[j] = pack2(acc[4 * tk + 2], acc[4 * tk + 3]);
    vhi[j] = movm(pack2(acc[4 * tv + 2], acc[4 * tv + 3]));
    qlo[j] = pack2(acc[4 * tq], acc[4 * tq + 1]);
    qhi[j] = pack2(acc[4 * tq + 2], acc[4 * tq + 3]);
    klo[j] = pack2(acc[4 * tk], acc[4 * tk + 1]);
    vlo[j] = pack2(acc[4 * tv], acc[4 * tv + 1]);
    asm volatile("" : "+r"(khi[j]), "+r"(qlo[j]), "+r"(qhi[j]), "+r"(klo[j]), "+r"(vlo[j]));
  }
}

template <int ROT> __device__ __forceinline__ void halo_send(const float* acc, uint4* ho, uint32_t tag) {
#pragma unroll
  for (int j = 0; j < 7; j++) {
    uint32_t x[3];
#pragma unroll
    for (int e = 0; e < 3; e++) {
      const int i = 3 * j + e, y = (i % 10 + ROT) % 10, tk = y < 8 ? 8 + y : 18 + y, tv = y < 8 ? 16 + y : 20 + y;
      x[e] = i < 10 ? pack2(acc[4 * tk + 2], acc[4 * tk + 3]) : i < 20 ? movm(pack2(acc[4 * tv + 2], acc[4 * tv + 3])) : 0u;
    }
    asm volatile("st.relaxed.gpu.global.v4.u32 [%0], {%1, %2, %3, %4};" ::"l"(ho + 32 * j), "r"(x[0]), "r"(x[1]), "r"(x[2]), "r"(tag) : "memory");
  }
}

__device__ __forceinline__ void attention(float* acc, uint32_t sb, int b, int par, int w, int lane, uint32_t tag) {
  const int g = lane >> 2, t = lane & 3;
  uint32_t klo[10], khi[10], vlo[10], vhi[10], qlo[10], qhi[10], kpv[10], vpv[10];
  if (w == 3 && b < NCTA - 8) {
    uint4* ho = g_halo + (b * 2 + par) * 224 + lane;
    if (tail_first(b & 7)) halo_send<8>(acc, ho, tag);
    else halo_send<0>(acc, ho, tag);
    TSIF(par == 0, 76);
    pin<120>(acc);
  }
  if (tail_first(b & 7)) pack_qkv<8>(acc, qlo, qhi, klo, khi, vlo, vhi);
  else pack_qkv<0>(acc, qlo, qhi, klo, khi, vlo, vhi);
  const uint32_t xa = sb + OFF_KVX + (par * 3) * 2560 + lane * 16;
  if (w < 3) {
    sts128(xa + w * 2560, khi[0], khi[1], khi[2], khi[3]);
    sts128(xa + w * 2560 + 512, khi[4], khi[5], khi[6], khi[7]);
    sts128(xa + w * 2560 + 1024, khi[8], khi[9], vhi[0], vhi[1]);
    sts128(xa + w * 2560 + 1536, vhi[2], vhi[3], vhi[4], vhi[5]);
    sts128(xa + w * 2560 + 2048, vhi[6], vhi[7], vhi[8], vhi[9]);
  }
  TSIF(par == 0 && w == 1, 64);
#pragma unroll
  for (int j = 0; j < 10; j++) vlo[j] = movm(vlo[j]);
  const bool far0 = 2 * t > g, far1 = 2 * t + 1 > g;
  const uint32_t mfar = (far0 ? 0x0000FFFFu : 0u) | (far1 ? 0xFFFF0000u : 0u);
  float slo[4][2], lg[2][2];
  uint32_t phi[4], plo[4], qml[4], qmh[4];
#pragma unroll
  for (int h = 0; h < 4; h++) {
    const int f = h == 0 ? 0 : h == 1 ? 3 : h == 2 ? 5 : 8, hf = h < 2 ? 2 : 7;
    const bool mine = (h & 1) ? t >= 2 : t < 2;
    qml[h] = mine ? qlo[hf] : 0u;
    qmh[h] = mine ? qhi[hf] : 0u;
    float a[4] = {0.f, 0.f, 0.f, 0.f}, c[4] = {0.f, 0.f, 0.f, 0.f};
    mma16816(a, qlo[f], qhi[f], qlo[f + 1], qhi[f + 1], klo[f], klo[f + 1]);
    mma16816(c, qlo[f], qhi[f], qlo[f + 1], qhi[f + 1], khi[f], khi[f + 1]);
    mma1688(a, qml[h], qmh[h], klo[hf]);
    mma1688(c, qml[h], qmh[h], khi[hf]);
    slo[h][0] = a[0];
    slo[h][1] = a[1];
    lg[h & 1][0] = far0 ? a[2] : c[2];
    lg[h & 1][1] = far1 ? a[3] : c[3];
    if (h & 1) softmax_two(lg, phi[h - 1], phi[h]);
  }
  TSIF(par == 0 && w == 1, 65);
  wg_sync(1 + par);
  TSIF(par == 0 && w == 1, 66);
  const bool nohist = (w == 0) && (b < 8);
  const uint4* hp = g_halo + ((b - 8) * 2 + par) * 224 + lane;
  uint32_t tg[7];
  if (w > 0) {
    const uint4 v0 = lds128(xa + (w - 1) * 2560), v1 = lds128(xa + (w - 1) * 2560 + 512), v2 = lds128(xa + (w - 1) * 2560 + 1024);
    const uint4 v3 = lds128(xa + (w - 1) * 2560 + 1536), v4 = lds128(xa + (w - 1) * 2560 + 2048);
    kpv[0] = v0.x; kpv[1] = v0.y; kpv[2] = v0.z; kpv[3] = v0.w; kpv[4] = v1.x; kpv[5] = v1.y; kpv[6] = v1.z; kpv[7] = v1.w;
    kpv[8] = v2.x; kpv[9] = v2.y; vpv[0] = v2.z; vpv[1] = v2.w; vpv[2] = v3.x; vpv[3] = v3.y; vpv[4] = v3.z; vpv[5] = v3.w;
    vpv[6] = v4.x; vpv[7] = v4.y; vpv[8] = v4.z; vpv[9] = v4.w;
  } else if (nohist) {
#pragma unroll
    for (int j = 0; j < 10; j++) kpv[j] = vpv[j] = 0u;
  } else {
    TSIF(par == 0, 77);
    halo_read(kpv, vpv, tg, hp);
  }
  if (w == 0 && !nohist) {
    int spins = 0;
    while (true) {
      bool ok = true;
#pragma unroll
      for (int j = 0; j < 7; j++) ok = ok && tg[j] == tag;
      if (__all_sync(0xffffffffu, ok) || ++spins > SPIN_LIMIT) break;
      halo_read(kpv, vpv, tg, hp);
    }
    TSIF(par == 0, 79);
  }
#pragma unroll
  for (int h = 0; h < 4; h++) {
    const int f = h == 0 ? 0 : h == 1 ? 3 : h == 2 ? 5 : 8, hf = h < 2 ? 2 : 7;
    float a[4] = {0.f, 0.f, 0.f, 0.f};
    mma16816(a, qlo[f], qhi[f], qlo[f + 1], qhi[f + 1], kpv[f], kpv[f + 1]);
    mma1688(a, qml[h], qmh[h], kpv[hf]);
    const float ninf = __int_as_float(0xff800000);
    lg[h & 1][0] = far0 ? (nohist ? ninf : a[0]) : slo[h][0];
    lg[h & 1][1] = far1 ? (nohist ? ninf : a[1]) : slo[h][1];
    if (h & 1) softmax_two(lg, plo[h - 1], plo[h]);
  }
  TSIF(par == 0 && w <= 1, 67 + w);
  uint32_t ov[20];
#pragma unroll
  for (int hp = 0; hp < 2; hp++) {
    const int hf = hp ? 7 : 2;
    float sh[4] = {0.f, 0.f, 0.f, 0.f}, i0 = 0.f, i1 = 0.f;
#pragma unroll
    for (int e = 0; e < 2; e++) {
      const int h = 2 * hp + e, f = h == 0 ? 0 : h == 1 ? 3 : h == 2 ? 5 : 8;
      const uint32_t a0 = plo[h] & mfar, a2 = plo[h] & ~mfar, a3 = phi[h] & mfar, c1 = phi[h] & ~mfar;
      float sum[4] = {0.f, 0.f, 0.f, 0.f};
      mma1688(sum, plo[h], phi[h], 0x3F803F80u);
      const float r0 = rcp(sum[0]), r1 = rcp(sum[2]);
#pragma unroll
      for (int j = f; j < f + 2; j++) {
        float o[4] = {0.f, 0.f, 0.f, 0.f};
        mma16816(o, a0, 0u, a2, a3, vpv[j], vlo[j]);
        mma1688(o, 0u, c1, vhi[j]);
        ov[2 * j] = pack2(o[0] * r0, o[1] * r0);
        ov[2 * j + 1] = pack2(o[2] * r1, o[3] * r1);
      }
      const bool mine = e ? g >= 4 : g < 4;
      mma16816(sh, a0, 0u, a2, a3, mine ? vpv[hf] : 0u, mine ? vlo[hf] : 0u);
      mma1688(sh, 0u, c1, mine ? vhi[hf] : 0u);
      if (e == 0 || t >= 2) {
        i0 = r0;
        i1 = r1;
      }
    }
    ov[2 * hf] = pack2(sh[0] * i0, sh[1] * i0);
    ov[2 * hf + 1] = pack2(sh[2] * i1, sh[3] * i1);
  }
  TS(32 + 4 * par + w);
  mbar_wait(sb + OFF_BAR + 8 * B_P1, 0);
  const uint32_t oa = sb + OFF_OA + (lane >> 4) * 2048 + (32 * w + 2 * (lane & 15) + par) * 16;
#pragma unroll
  for (int j = 0; j < 5; j++) stsm4(oa + 4096 * j, ov + 4 * j);
  TSIF(par == 0 && w == 0, 120);
  fence_async_smem();
  TSIF(par == 0 && w == 0, 121);
  __syncwarp();
  if (lane == 0) mbar_arrive(sb + OFF_BAR + 8 * B_ATTN);
  TSM(w == 0 || w == 2, 122 + par + (w == 2 ? 3 : 0));
}

struct Maps {
  CUtensorMap x, wm, wt, k, v, y, wo, qm, qt, om, ot, yl, ol;
};

__device__ __forceinline__ void load_stage(uint32_t sb, int kb, int b, const Maps& m) {
  const uint32_t st = sb + (kb & 3) * STAGE_BYTES, bar = sb + OFF_BAR + 8 * (B_FULL1 + (kb & 3));
  const int r = b >> 3, hg = b & 7, slab = kb - KV_KB;
  const bool kv = slab >= 0 && slab < 5;
  const uint32_t kbar = sb + OFF_BAR + 8 * (B_KV + slab), dst = sb + OFF_KVS + slab * KVS_BYTES;
  mbar_expect_tx(bar, STAGE_BYTES);
  if (kv) mbar_expect_tx(kbar, KVS_BYTES);
  tma_3d(st, &m.x, 64 * kb, 64 * r, 0, bar);
  tma_3d(st + ST_W, &m.wm, 80 * hg + (tail_first(hg) ? 16 : 0), 64 * kb, 0, bar);
  tma_3d(st + ST_WT, &m.wt, 80 * hg + (tail_first(hg) ? 0 : 64), 64 * kb, 0, bar);
  if (kv) tma_3d(dst, &m.k, 0, 32 * (b >> 1) - 3, 2 * slab + (b & 1), kbar);
  if (kv) tma_3d(dst + KVS_V, &m.v, 0, 32 * (b >> 1), 2 * slab + (b & 1), kbar);
}

__global__ void __launch_bounds__(NTHR, 1) fused_kernel(const __grid_constant__ Maps m, const Params p) {
  extern __shared__ __align__(1024) uint8_t smem[];
  const uint32_t sb = (uint32_t)__cvta_generic_to_shared(smem);
  const uint32_t bars = sb + OFF_BAR;
  const int tid = threadIdx.x, lane = tid & 31;
  int b = blockIdx.x;
  b = (((b & 63) >> 3) * 2 + (b & 1)) * 8 + (((b < 64 ? 0x6521 : 0x7430) >> (4 * ((b >> 1) & 3))) & 7);
  const int r = b >> 3, hg = b & 7;

  if (tid == T_ISSUE) {
    TSM(true, 0);
    mbar_init(bars + 8 * B_F0, 1);
    fence_async_smem();
    mbar_expect_tx(bars + 8 * B_F0, ST_WT);
    tma_3d(sb, &m.x, 0, 64 * r, 0, bars + 8 * B_F0);
    tma_3d(sb + ST_W, &m.wm, 80 * hg + (tail_first(hg) ? 16 : 0), 0, 0, bars + 8 * B_F0);
#pragma unroll
    for (int i = 0; i < 4; i++) mbar_init(bars + 8 * (B_FULL1 + i), 1);
    fence_async_smem();
    if (BAD_DELAY && blockIdx.x < 64) {
      const long long t0 = clock64();
      while (clock64() - t0 < BAD_DELAY) {}
    }
    mbar_expect_tx(bars + 8 * B_FULL1, STAGE_BYTES - ST_WT);
    tma_3d(sb + ST_WT, &m.wt, 80 * hg + (tail_first(hg) ? 0 : 64), 0, 0, bars + 8 * B_FULL1);
    if (BAD_DELAY2 && blockIdx.x < 64) {
      const long long t0 = clock64();
      while (clock64() - t0 < BAD_DELAY2) {}
    }
    load_stage(sb, 1, b, m);
  } else if (tid == T_INIT) {
#pragma unroll
    for (int i = 0; i < B_F0; i++) mbar_init(bars + 8 * i, i < B_GATE ? 8 : i < B_CVD ? 4 : i == B_CVD ? 20 : 1);
    fence_async_smem();
  }
  const int warp = __shfl_sync(0xffffffffu, tid >> 5, 0), wg = warp >> 2, w = warp & 3;
  __syncthreads();

  if (wg == 3) {
    asm volatile("setmaxnreg.dec.sync.aligned.u32 56;");
    if (w == 0) {
      if (lane == 0) {
#pragma unroll 1
        for (int kb = 2; kb < 10; kb++) {
          if (kb >= 4) mbar_wait(bars + 8 * (kb == 7 ? B_E3 : B_EMPTY1 + (kb & 3)), (kb >> 3) & 1);
          TSIF(kb >= 4, 44 + kb);
          load_stage(sb, kb, b, m);
          TSIF(kb == 3, 60);
          if (kb == 9) mbar_arrive(bars + 8 * B_LAST);
        }
        mbar_wait(bars + 8 * B_WOP, 0);
        mbar_wait(bars + 8 * B_EPOCH, 0);
        flag_wait(g_cnt + C_W + 32 * hg, (lds32(sb + OFF_EPOCH) + 1) * 16);
        TS(30);
#pragma unroll 1
        for (int j = 0; j < 8; j++) {
          if (j >= 6) mbar_wait(bars + 8 * (B_EMPTY2 + j - 6), 0);
          if (j == 4) mbar_wait(bars + 8 * B_ORB, 0);
          TSIF(j >= 6, 100 + j);
          mbar_expect_tx(bars + 8 * (B_FULL2 + j), j == 0 ? WO_BYTES : j == 5 ? O_BYTES + WO_BYTES + 512 : O_BYTES + WO_BYTES);
          bulk_load(sb + off_w(j), g_WO + (hg * 8 + step_src(hg, j)) * 800, WO_BYTES, bars + 8 * (B_FULL2 + j));
        }
        mbar_wait(bars + 8 * (B_EMPTY2 + 3), 0);
        mbar_expect_tx(bars + 8 * B_QF, O_BYTES);
        tma_2d(sb + OFF_QS, &m.qm, 80 * hg, 128 * r, bars + 8 * B_QF);
        tma_2d(sb + OFF_QT, &m.qt, 80 * hg + 64, 128 * r, bars + 8 * B_QF);
      }
    } else if (w == 1) {
      unsigned epoch = 0;
      if (lane == 0) {
        epoch = atomicAdd(g_cnt + C_LAUNCH, 1u) / NCTA;
        asm volatile("st.shared.u32 [%0], %1;" ::"r"(sb + OFF_EPOCH), "r"(epoch) : "memory");
        mbar_arrive(bars + 8 * B_EPOCH);
        mbar_wait(bars + 8 * B_KVD, 0);
        mbar_expect_tx(bars + 8 * B_HB, 5 * 4096);
#pragma unroll 1
        for (int c = 0; c < 5; c++) {
          if (c == 3) mbar_wait(bars + 8 * B_S3, 0);
          bulk_load(sb + off_ch(c) + U_BYTES, p.ssm_k + (5 * b + c) * SEQ, 4096, bars + 8 * B_HB);
        }
#pragma unroll
        for (int c = 0; c < 4; c++) mbar_expect_tx(bars + 8 * (B_U + c), c < 3 ? U_BYTES : 2 * U_BYTES);
        const uint4* usrc = g_U + 5 * b * U_PITCH;
        mbar_wait(bars + 8 * B_USIG, 0);
        flag_wait(g_cnt + C_PREP + 32 * (b & 15), (epoch + 1) * NCTA);
        TS(23);
#pragma unroll
        for (int c = 0; c < 5; c++) {
          if (c == 3) mbar_wait(bars + 8 * (B_U + 2), 0);
          bulk_load(sb + off_ch(c), usrc + c * U_PITCH, U_BYTES, bars + 8 * (B_U + (c < 3 ? c : 3)));
          TSIF(c == 0 || c == 4, 116 + (c >> 2));
        }
      }
      epoch = __shfl_sync(0xffffffffu, epoch, 0);
      if (lane < 8) {
        const int src = (b & ~7) | step_src(hg, lane);
        mbar_wait(bars + 8 * B_ATTN, 0);
        TS(20);
        bool seen = false;
#pragma unroll 1
        for (int spins = 0; spins < SPIN_LIMIT; spins++) {
          const bool now = !seen && (int)(flag_read(g_cnt + C_O + 32 * src) - (epoch + 1)) >= 0;
          if (now && lane >= 1 && lane < 4) bulk_load(sb + off_o(lane), g_O + src * 1280, O_BYTES, bars + 8 * (B_FULL2 + lane));
          seen = seen || now;
          if (__all_sync(0xff, seen)) break;
        }
        TS(21);
        if (lane == 5) bulk_load(sb + OFF_GATE, g_gate + 128 * r, 512, bars + 8 * (B_FULL2 + 5));
#pragma unroll 1
        for (int j = 4; j < 8; j++) {
          if (lane == j) {
            mbar_wait(bars + 8 * (j < 6 ? B_C34 : B_EMPTY2 + j - 6), 0);
            bulk_load(sb + off_o(j), g_O + src * 1280, O_BYTES, bars + 8 * (B_FULL2 + j));
          }
          __syncwarp(0xff);
        }
        TS(22);
      }
    } else if (w == 2) {
      mbar_wait(bars + 8 * B_PREP, 0);
      flag_signal(g_cnt + C_PREP, 16, lane);
      TS(25);
      if (lane == 0) {
        mbar_arrive(bars + 8 * B_USIG);
        mbar_expect_tx(bars + 8 * B_ORB, O_BYTES / 4 + 64);
        mbar_wait(bars + 8 * B_GATE, 0);
        publish(g_gate + 16 * b, sb + OFF_GATE + 64 * hg, 64);
        bulk_load(sb + OFF_GATE + 64 * hg, g_gate + 16 * b, 64, bars + 8 * B_ORB);
        mbar_wait(bars + 8 * B_ATTN, 0);
        publish(g_O + b * 1280, sb + OFF_OA, O_BYTES);
        tma_2d(sb + OFF_KVX + 10240, &m.ol, 48, b * 160, bars + 8 * B_ORB);
        TS(74);
        mbar_wait(bars + 8 * B_ORB, 0);
        flag_bump(g_cnt + C_O + 32 * b);
        TS(26);
      }
    } else {
      if (lane == 0) {
        uint4* dst = g_WO + (hg * 8 + (r >> 1)) * 800 + (r & 1) * 80;
        mbar_wait(bars + 8 * B_S3, 0);
        asm volatile("cp.async.bulk.prefetch.L2.global [%0], 6400;" ::"l"(p.wo + b * 3200) : "memory");
        mbar_wait(bars + 8 * B_P1, 0);
        mbar_wait(bars + 8 * WB_TRIG, 0);
        mbar_expect_tx(bars + 8 * B_WST, WO_BYTES / 2);
        tma_3d(sb + OFF_WA, &m.wo, 0, 40 * r, 5 * hg, bars + 8 * B_WST);
        mbar_wait(bars + 8 * B_WST, 0);
#pragma unroll 1
        for (int n = 0; n < 5; n++) bulk_store(dst + 160 * n, sb + OFF_WA + 1280 * n, 1280);
        bulk_wait_read();
        mbar_expect_tx(bars + 8 * B_WST, WO_BYTES / 2);
#pragma unroll 1
        for (int n = 0; n < 5; n++) bulk_load(sb + OFF_WA + 1280 * n, dst + 160 * n, 1280, bars + 8 * B_WST);
        mbar_wait(bars + 8 * B_WST, 1);
        flag_bump(g_cnt + C_W + 32 * hg);
        mbar_arrive(bars + 8 * B_WOP);
        TS(71);
        mbar_expect_tx(bars + 8 * B_C34, 3 * (U_BYTES / 4));
        mbar_expect_tx(bars + 8 * B_YRB, 2 * (U_BYTES / 4));
#pragma unroll 1
        for (int c = 0; c < 5; c++) {
          mbar_wait(bars + 8 * (B_YST + c), 0);
          publish(g_U + (5 * b + c) * U_PITCH, sb + off_ch(c), U_BYTES);
          tma_2d(sb + off_ch(c), &m.yl, 48, (5 * b + c) * (U_PITCH / 8), bars + 8 * (c < 3 ? B_C34 : B_YRB));
        }
        TS(75);
        mbar_wait(bars + 8 * B_C34, 0);
        mbar_wait(bars + 8 * B_YRB, 0);
        flag_bump(g_cnt + C_Y + 32 * (b >> 4));
        TS(27);
        mbar_expect_tx(bars + 8 * B_YFULL, 20480);
        flag_wait(g_cnt + C_Y + 32 * hg, (lds32(sb + OFF_EPOCH) + 1) * 16);
        TS(24);
        tma_2d(sb + OFF_YT, &m.y, 128 * r, 80 * hg, bars + 8 * B_YFULL);
        tma_2d(sb + OFF_YT + 10240, &m.y, 128 * r + 64, 80 * hg, bars + 8 * B_YFULL);
      }
    }
  } else {
    asm volatile("setmaxnreg.inc.sync.aligned.u32 152;");
    if (wg < 2) {
      float acc[120];
#pragma unroll
      for (int i = 0; i < 120; i++) acc[i] = 0.f;
      const uint32_t da = desc_lo(sb + wg * 8192, 16), db = desc_lo(sb + ST_W, 8192), dc = desc_lo(sb + ST_WT, 2048);
      mbar_wait(bars + 8 * B_F0, 0);
      TSIF(w == 0 && wg == 0, 1);
      wg_fence();
#pragma unroll
      for (int k = 0; k < 4; k++) WgSST<192>::mma<HI_SW128, HI_SW128>(acc, da + 2 * k, db + 128 * k, 1);
      wg_commit();
      mbar_wait(bars + 8 * B_FULL1, 0);
      wg_fence();
#pragma unroll
      for (int k = 0; k < 4; k++) WgSST<48>::mma<HI_SW128, HI_SW32>(acc + 96, da + 2 * k, dc + 32 * k, 1);
      wg_commit();
#pragma unroll 1
      for (int kb = 1; kb < 10; kb++) {
        mbar_wait(bars + 8 * (B_FULL1 + (kb & 3)), (kb >> 2) & 1);
        const uint32_t so = (kb & 3) * (STAGE_BYTES >> 4);
        wg_fence();
#pragma unroll
        for (int k = 0; k < 4; k++) {
          WgSST<192>::mma<HI_SW128, HI_SW128>(acc, da + so + 2 * k, db + so + 128 * k, 1);
          WgSST<48>::mma<HI_SW128, HI_SW32>(acc + 96, da + so + 2 * k, dc + so + 32 * k, 1);
        }
        wg_commit();
        wg_wait<1>();
        if (lane == 0) mbar_arrive(bars + 8 * (kb == 4 ? B_E3 : B_EMPTY1 + ((kb - 1) & 3)));
      }
      mbar_wait(bars + 8 * B_EPOCH, 0);
      const uint32_t tag = lds32(sb + OFF_EPOCH) + 1;
      mbar_wait(bars + 8 * B_S3, 0);
      wg_wait<0>();
      pin<120>(acc);
      if (lane == 0) mbar_arrive(bars + 8 * B_P1);
      TSM(w == 0, 3 + wg);
      attention(acc, sb, b, wg, w, lane, tag);
    } else {
      const int tw = tid & 127, chl = 64 * (b & 1) + 8 * w + (lane >> 2);
      uint4* up = g_U + chl * U_PITCH + ((4 * (b >> 1) + (lane & 3)) ^ ((b >> 2) & 1));
      uint2 sw[10];
      uint32_t dv = 0;
      if (lane < 5) dv = __ldg(reinterpret_cast<const unsigned short*>(p.ssm_D) + 5 * b + lane);
#pragma unroll
      for (int i = 0; i < 10; i++) sw[i] = ldg64(reinterpret_cast<const uint2*>(p.shift_k) + chl + 128 * (i >> 1) + 32 * (i & 1));
      uint32_t tab[12];
      uint32_t tt[2];
      fft_tables(tab, tw);
      fft_twiddles(tt, tw);
      uint4 res[10];
#pragma unroll
      for (int i = 0; i < 10; i++) res[i] = make_uint4(0, 0, 0, 0);
#pragma unroll 1
      for (int slab = 0; slab < 5; slab++) {
#pragma unroll
        for (int i = 0; i < 8; i++) res[i] = res[i + 2];
        prep_slab(res + 8, sw, sb, slab, w, lane);
        TSIF(w == 0, 99 + 4 * slab);
#pragma unroll
        for (int i = 0; i < 8; i++) sw[i] = sw[i + 2];
      }
      TSIF(w == 0, 28);
      __syncwarp();
      if (lane == 0) mbar_arrive(bars + 8 * B_KVD + ((res[8].x ^ res[9].x) & p.zero));
      mbar_wait(bars + 8 * B_KVD, 0);
      fft_tables_store(tab, sb, tw);
      mbar_wait(bars + 8 * B_LAST, 0);
#pragma unroll
      for (int i = 0; i < 10; i++) up[(128 * (i >> 1) + 32 * (i & 1)) * U_PITCH] = res[i];
      __syncwarp();
      if (lane == 0) mbar_arrive(bars + 8 * B_PREP);
      TSIF(w == 0, 5);
      mbar_wait(bars + 8 * B_LAST, 0);
      prep_gate(p, sb, b, w, lane);
      __syncwarp();
      if (lane == 0) mbar_arrive(bars + 8 * B_GATE);
      TSIF(w == 0, 72);
      mbar_wait(bars + 8 * B_HB, 0);
      TSIF(w == 0, 2);
      const uint32_t ha = sb + U_BYTES + ((tw >> 3) * 16 + 8 + (tw & 7)) * 16;
      uint4 hv[5];
#pragma unroll
      for (int c = 0; c < 5; c++) hv[c] = lds128(ha + off_ch(c));
      __syncwarp();
#pragma unroll
      for (int c = 0; c < 5; c++) sts128((ha ^ 16) + off_ch(c), hv[c].x, hv[c].y, hv[c].z, hv[c].w);
      asm volatile("st.shared.v2.u32 [%0], {%1, %2};" ::"r"(sb + OFF_TT + 8 * tw), "r"(tt[0]), "r"(tt[1]) : "memory");
      if (tw < 5) asm volatile("st.shared.f32 [%0], %1;" ::"r"(sb + OFF_D + 4 * tw), "f"(bf_lo(dv) * 0.125f) : "memory");
      fence_async_smem();
      __syncwarp();
      if (lane == 0) mbar_arrive(bars + 8 * B_HA);
      TSIF(w == 0, 6);
    }

    FftConst fc;
    TSM(w == 0 && wg == 0, 104);
    mbar_wait(bars + 8 * B_HA, 0);
    fft_matrices(fc, sb, w, lane);
    TSM(w == 0 && wg == 0, 105);
    TSM(w == 0 && wg == 2, 124);
#pragma unroll 1
    for (uint32_t tasks = wg == 0 ? TASK0 : wg == 1 ? TASK1 : TASK2; tasks; tasks >>= 4) {
      const int c = (tasks & 7) - 1;
      conv_channel(fc, sb, c, wg, w, lane);
      if (lane == 0) mbar_arrive(bars + 8 * (B_YST + c));
      TSM(w == 0, 10 + c);
    }

    if (wg != 1) {
      const int wg = warp >> 3;
      const int g = lane >> 2;
      float acc[40];
#pragma unroll
      for (int i = 0; i < 40; i++) acc[i] = 0.f;
      const uint32_t da = desc_lo(sb + wg * 1024, 2048), db = desc_lo(sb, 2560);
      mbar_wait(bars + 8 * B_ORB, 0);
      mbar_wait(bars + 8 * B_FULL2, 0);
      TSM(w == 0, 15 + wg);
#pragma unroll 1
      for (int j = 0; j < 8; j++) {
        if (j == 1 - wg) mbar_wait(bars + 8 * B_CVD, 0);
        mbar_wait(bars + 8 * (B_FULL2 + j), 0);
        TSM(w == 0 && wg == 0, 44 + (j < 4 ? j : j + 6));
        const uint32_t oa = da + (off_o(j) >> 4), ob = db + (off_w(j) >> 4);
        wg_fence();
#pragma unroll
        for (int k = 0; k < 5; k++) WgSST<80>::mma<HI_NONE, HI_SW32>(acc, oa + 256 * k, ob + 32 * k, 1);
        wg_commit();
        wg_wait<1>();
        if (j >= 1 && j <= 4 && lane == 0) mbar_arrive(bars + 8 * (B_EMPTY2 + j - 1));
      }
      TSIF(w == 0 && wg == 0, 113);
      const int tr = 64 * wg + 16 * w + (lane & 15);
      const uint32_t fm = sb + OFF_QS + tr * 128, fx = (lane >> 4) ^ (tr & 7);
      const uint32_t ft = sb + OFF_QT + tr * 32 + (((lane >> 4) ^ (tr >> 2)) & 1) * 16;
      const float g0 = __uint_as_float(lds32(sb + OFF_GATE + (64 * wg + 16 * w + g) * 4));
      const float g1 = __uint_as_float(lds32(sb + OFF_GATE + (64 * wg + 16 * w + 8 + g) * 4));
      const uint32_t ga = pack2(g0, g0), gb = pack2(g1, g1);
      const uint32_t na = pack2(1.f - g0, 1.f - g0), nb = pack2(1.f - g1, 1.f - g1);

      uint32_t qf[20];
      mbar_wait(bars + 8 * B_QF, 0);
      TSM(w == 0 && wg == 0, 99);
#pragma unroll
      for (int j = 0; j < 5; j++) ldsm4(qf + 4 * j, j < 4 ? fm + ((fx ^ (2 * j)) << 4) : ft);
#pragma unroll
      for (int i = 0; i < 20; i++) {
        qf[i] = bmul((i & 1) ? gb : ga, qf[i]);
        asm volatile("" : "+r"(qf[i]));
      }

      wg_wait<0>();
      pin<40>(acc);
      TSM(w == 0, 17 + wg);
      uint32_t pb[20];
#pragma unroll
      for (int j = 0; j < 10; j++) {
        pb[2 * j] = bmul(na, pack2(acc[4 * j], acc[4 * j + 1]));
        pb[2 * j + 1] = bmul(nb, pack2(acc[4 * j + 2], acc[4 * j + 3]));
        asm volatile("" : "+r"(pb[2 * j]), "+r"(pb[2 * j + 1]));
      }
      const uint32_t ya = sb + OFF_YT + wg * 10240 + ((lane >> 4) * 8 + (lane & 7)) * 128 +
                          (((2 * w + (((lane >> 3) & 1) ^ wg)) ^ (lane & 7)) << 4);
      mbar_wait(bars + 8 * B_YFULL, 0);
      TSM(w == 0 && wg == 0, 19);
#pragma unroll
      for (int j = 0; j < 5; j++) {
        uint32_t y[4];
        ldsm4t(y, ya + 2048 * j);
#pragma unroll
        for (int i = 0; i < 4; i++)
          qf[4 * j + i] = bfma(qf[4 * j + i], y[i], pb[4 * j + i]);
      }
#pragma unroll
      for (int j = 0; j < 5; j++) stsm4(j < 4 ? fm + ((fx ^ (2 * j)) << 4) : ft, qf + 4 * j);
      fence_async_smem();
      __syncwarp();
      if (lane == 0) {
        const int row = 64 * wg + 16 * w;
        asm volatile("cp.async.bulk.tensor.2d.global.shared::cta.bulk_group [%0, {%2, %3}], [%1];"
                     ::"l"(&m.om), "r"(sb + OFF_QS + row * 128), "r"(80 * hg), "r"(128 * r + row) : "memory");
        asm volatile("cp.async.bulk.tensor.2d.global.shared::cta.bulk_group [%0, {%2, %3}], [%1];"
                     ::"l"(&m.ot), "r"(sb + OFF_QT + row * 32), "r"(80 * hg + 64), "r"(128 * r + row) : "memory");
        asm volatile("cp.async.bulk.commit_group;\ncp.async.bulk.wait_group.read 0;" ::: "memory");
      }
      TSM(w == 0 || w == 3, 40 + 2 * wg + (w & 1));
    }
  }
}

typedef CUresult (*EncodeFn)(CUtensorMap*, CUtensorMapDataType, cuuint32_t, void*, const cuuint64_t*, const cuuint64_t*,
                             const cuuint32_t*, const cuuint32_t*, CUtensorMapInterleave, CUtensorMapSwizzle,
                             CUtensorMapL2promotion, CUtensorMapFloatOOBfill);

void encode(EncodeFn fn, CUtensorMap* tm, const void* base, int rank, const cuuint64_t* dims, const cuuint64_t* strides,
            const cuuint32_t* box, CUtensorMapSwizzle swz) {
  const cuuint32_t ones[3] = {1, 1, 1};
  fn(tm, CU_TENSOR_MAP_DATA_TYPE_BFLOAT16, rank, const_cast<void*>(base), dims, strides, box, ones,
     CU_TENSOR_MAP_INTERLEAVE_NONE, swz, CU_TENSOR_MAP_L2_PROMOTION_L2_128B, CU_TENSOR_MAP_FLOAT_OOB_FILL_NONE);
}

}

extern "C" void kernel_launch(void* const* d_in, const int* in_sizes, int n_in, void* d_out, int out_size) {
  (void)in_sizes; (void)n_in; (void)out_size;
  Params p;
  p.q = (const __nv_bfloat16*)d_in[0];
  p.k = (const __nv_bfloat16*)d_in[1];
  p.v = (const __nv_bfloat16*)d_in[2];
  p.shift_k = (const __nv_bfloat16*)d_in[3];
  p.ssm_k = (const __nv_bfloat16*)d_in[4];
  p.ssm_D = (const __nv_bfloat16*)d_in[5];
  p.wqkv = (const __nv_bfloat16*)d_in[7];
  p.wo = (const __nv_bfloat16*)d_in[8];
  p.gate_w = (const __nv_bfloat16*)d_in[9];
  p.out = (__nv_bfloat16*)d_out;
  p.zero = 0;

  static EncodeFn fn = nullptr;
  static void *yaddr = nullptr, *oaddr = nullptr;
  if (!fn) {
    cudaDriverEntryPointQueryResult qr;
    void* f = nullptr;
    cudaGetDriverEntryPoint("cuTensorMapEncodeTiled", &f, cudaEnableDefault, &qr);
    fn = (EncodeFn)f;
    cudaGetSymbolAddress(&yaddr, g_U);
    cudaGetSymbolAddress(&oaddr, g_O);
    cudaFuncSetAttribute(fused_kernel, cudaFuncAttributeMaxDynamicSharedMemorySize, SMEM_BYTES);
  }
  Maps m;
  {
    const cuuint64_t dims[3] = {640, 1024, 2}, st[2] = {2560, 1280};
    const cuuint32_t box[3] = {64, 64, 2};
    encode(fn, &m.x, p.q, 3, dims, st, box, CU_TENSOR_MAP_SWIZZLE_128B);
  }
  {
    const cuuint64_t dims[3] = {640, 640, 3}, st[2] = {3840, 1280};
    const cuuint32_t box[3] = {64, 64, 3}, boxt[3] = {16, 64, 3};
    encode(fn, &m.wm, p.wqkv, 3, dims, st, box, CU_TENSOR_MAP_SWIZZLE_128B);
    encode(fn, &m.wt, p.wqkv, 3, dims, st, boxt, CU_TENSOR_MAP_SWIZZLE_32B);
  }
  {
    const cuuint64_t dims[3] = {64, 2048, 10}, st[2] = {1280, 128};
    const cuuint32_t boxk[3] = {64, 35, 1}, boxv[3] = {64, 32, 1};
    encode(fn, &m.k, p.k, 3, dims, st, boxk, CU_TENSOR_MAP_SWIZZLE_128B);
    encode(fn, &m.v, p.v, 3, dims, st, boxv, CU_TENSOR_MAP_SWIZZLE_128B);
  }
  {
    const cuuint64_t dims[3] = {16, 640, 40}, st[2] = {1280, 32};
    const cuuint32_t box[3] = {16, 40, 5};
    encode(fn, &m.wo, p.wo, 3, dims, st, box, CU_TENSOR_MAP_SWIZZLE_32B);
  }
  {
    const cuuint64_t dims[2] = {2048, 640}, st[1] = {U_PITCH * 16};
    const cuuint32_t box[2] = {64, 80};
    encode(fn, &m.y, yaddr, 2, dims, st, box, CU_TENSOR_MAP_SWIZZLE_128B);
    const cuuint64_t dl[2] = {64, DIM * U_PITCH / 8}, dol[2] = {64, NCTA * 160}, sl[1] = {128};
    const cuuint32_t bl[2] = {16, 32}, bol[2] = {16, 160};
    encode(fn, &m.yl, yaddr, 2, dl, sl, bl, CU_TENSOR_MAP_SWIZZLE_NONE);
    encode(fn, &m.ol, oaddr, 2, dol, sl, bol, CU_TENSOR_MAP_SWIZZLE_NONE);
  }
  {
    const cuuint64_t dims[2] = {640, 2048}, st[1] = {1280};
    const cuuint32_t bqm[2] = {64, 128}, bqt[2] = {16, 128}, bom[2] = {64, 16}, bot[2] = {16, 16};
    encode(fn, &m.qm, p.q, 2, dims, st, bqm, CU_TENSOR_MAP_SWIZZLE_128B);
    encode(fn, &m.qt, p.q, 2, dims, st, bqt, CU_TENSOR_MAP_SWIZZLE_32B);
    encode(fn, &m.om, p.out, 2, dims, st, bom, CU_TENSOR_MAP_SWIZZLE_128B);
    encode(fn, &m.ot, p.out, 2, dims, st, bot, CU_TENSOR_MAP_SWIZZLE_32B);
  }
  fused_kernel<<<NCTA, NTHR, SMEM_BYTES>>>(m, p);
}
```

```cpp
#include <cuda.h>
#include <cuda_bf16.h>
#include <cuda_runtime.h>
#include <stdint.h>

namespace {

constexpr int SEQ = 2048, DIM = 640, NCTA = 128, NTHR = 512;

#define KV_KB 2
#define DEV_EXIT 0
#define FENCE_LO 0
#define FENCE_HI 0
#define WB_TRIG B_USIG
#define T_ISSUE 288
#define HLIST 0x54132
#define T_INIT 448
#define TASK0 0x3
#define TASK1 0x52
#define TASK2 0x41

constexpr uint32_t STAGE_BYTES = 47104, ST_W = 16384, ST_WT = 40960;
constexpr uint32_t O_BYTES = 20480, WO_BYTES = 12800;
constexpr uint32_t OFF_OA = 0;
constexpr uint32_t OFF_QS = 3 * O_BYTES, OFF_QT = OFF_QS + 16384;
constexpr uint32_t OFF_WC = 81920;
constexpr uint32_t OFF_WA = 94720;
constexpr uint32_t OFF_GATE = 145920;
constexpr uint32_t OFF_TT = 146432;
constexpr uint32_t OFF_KVX = 148480;
constexpr uint32_t OFF_CH3 = 163840;
constexpr uint32_t CH_BYTES = 12288, U_BYTES = 4096;
constexpr uint32_t OFF_FT = 225280, OFF_GT = 229376;
constexpr uint32_t OFF_CH0 = 188416;
constexpr uint32_t OFF_KVS = OFF_CH0, KVS_V = 4480, KVS_BYTES = 8576;
constexpr uint32_t OFF_YT = 163840;
constexpr uint32_t OFF_BAR = 231936;
constexpr uint32_t SMEM_BYTES = OFF_BAR + 512;

enum : uint32_t {
  B_EMPTY1 = 0, B_S3 = 3, B_E3 = 4, B_EMPTY2 = 5, B_ATTN = 9, B_P1 = 10,
  B_GATE = 11, B_HA = 12, B_KVD = 13, B_PREP = 14, B_YST = 15, B_H = 20,
  B_CVD = 25,
  B_FULL2 = 26, B_U = 34, B_KV = 38, B_HB = 43, B_C34 = 44, B_YRB = 45, B_YFULL = 46, B_EPOCH = 47, B_LAST = 48,
  B_WOP = 49, B_USIG = 50, B_WST = 51, B_QF = 52, B_ORB = 53,
  B_F0 = 54, B_FULL1 = 55
};
constexpr uint32_t OFF_EPOCH = OFF_BAR + 8 * 59, OFF_D = OFF_BAR + 8 * 60;
__device__ __forceinline__ uint32_t off_o(int j) { return j < 4 ? OFF_OA + j * O_BYTES : j < 6 ? OFF_CH0 + (j - 4) * O_BYTES : OFF_OA + (j - 6) * O_BYTES; }
__device__ __forceinline__ uint32_t off_w(int j) { return j < 4 ? OFF_WA + j * WO_BYTES : j == 4 ? OFF_KVX : j == 5 ? OFF_WC : OFF_WA + (j - 6) * WO_BYTES; }
__device__ __forceinline__ int step_src(int hg, int j) { return j == 0 ? hg : j <= hg ? j - 1 : j; }
__device__ __forceinline__ bool tail_first(int hg) { return (hg & 3) == 3; }
__device__ __forceinline__ uint32_t off_ch(int c) { return (c < 3 ? OFF_CH0 : OFF_CH3 - 3 * CH_BYTES) + c * CH_BYTES; }

#define U_PITCH 264
__device__ __align__(1024) uint4 g_U[DIM * U_PITCH];
__device__ __align__(128) uint4 g_O[NCTA * 1280];
__device__ uint4 g_WO[64 * 800];
__device__ uint4 g_halo[NCTA * 2 * 7 * 32];
__device__ __align__(128) float g_gate[SEQ];
__device__ unsigned g_cnt[32 * (1 + 2 * 16 + 8 + NCTA)];
constexpr int C_LAUNCH = 0, C_PREP = 32, C_Y = 32 * 17, C_W = 32 * 33, C_O = 32 * 41;

#define TSM(cond, slot) do { } while (0)
#define TSIF(cond, slot) do { if (__LINE__ >= FENCE_LO && __LINE__ < FENCE_HI) sched_fence(); } while (0)
__device__ __forceinline__ void sched_fence() {
  asm volatile("{\n.reg .pred p;\n.reg .u32 c;\nmov.u32 c, %%clock;\nsetp.eq.u32 p, c, 0;\n@p st.shared.u32 [%0], c;\n}"
               ::"r"(1024 + OFF_EPOCH + 4) : "memory");
}
#define TS(slot) TSIF(true, slot)

struct Params {
  const __nv_bfloat16 *q, *k, *v, *shift_k, *ssm_k, *ssm_D, *wqkv, *wo, *gate_w;
  __nv_bfloat16* out;
  uint32_t zero;
};

constexpr int SPIN_LIMIT = 1 << 17;

__device__ __forceinline__ void mbar_init(uint32_t bar, uint32_t count) {
  asm volatile("mbarrier.init.shared::cta.b64 [%0], %1;" ::"r"(bar), "r"(count) : "memory");
}
__device__ __forceinline__ void mbar_expect_tx(uint32_t bar, uint32_t bytes) {
  asm volatile("mbarrier.arrive.expect_tx.shared::cta.b64 _, [%0], %1;" ::"r"(bar), "r"(bytes) : "memory");
}
__device__ __forceinline__ void mbar_arrive(uint32_t bar) {
  asm volatile("mbarrier.arrive.shared::cta.b64 _, [%0];" ::"r"(bar) : "memory");
}
__device__ __forceinline__ void mbar_wait(uint32_t bar, uint32_t parity) {
  uint32_t ok;
  int spins = 0;
  do {
      asm volatile("{\n.reg .pred p;\nmbarrier.try_wait.parity.shared::cta.b64 p, [%1], %2;\nselp.b32 %0, 1, 0, p;\n}"
                   : "=r"(ok) : "r"(bar), "r"(parity) : "memory");
    if (++spins > SPIN_LIMIT) break;
  } while (!ok);
}
__device__ __forceinline__ unsigned flag_read(const unsigned* p) {
  unsigned v;
  asm volatile("ld.relaxed.gpu.global.u32 %0, [%1];" : "=r"(v) : "l"(p) : "memory");
  return v;
}
__device__ __forceinline__ void flag_poll(const unsigned* p, unsigned target) {
  unsigned v;
  int spins = 0;
  do {
    asm volatile("ld.relaxed.gpu.global.u32 %0, [%1];" : "=r"(v) : "l"(p) : "memory");
    if (++spins > SPIN_LIMIT) break;
  } while ((int)(v - target) < 0);
}
__device__ __forceinline__ void flag_wait(const unsigned* p, unsigned target) {
  flag_poll(p, target);
}
__device__ __forceinline__ void flag_signal(unsigned* p, int n, int lane) {
  if (lane == 0) asm volatile("fence.release.gpu;" ::: "memory");
  __syncwarp();
  if (lane < n) asm volatile("red.relaxed.gpu.global.add.u32 [%0], 1;" ::"l"(p + 32 * lane) : "memory");
}
__device__ __forceinline__ void flag_bump(unsigned* p) {
  asm volatile("red.relaxed.gpu.global.add.u32 [%0], 1;" ::"l"(p) : "memory");
}
__device__ __forceinline__ void fence_async_smem() { asm volatile("fence.proxy.async.shared::cta;" ::: "memory"); }
__device__ __forceinline__ void wg_sync(int id) { asm volatile("bar.sync %0, 128;" ::"r"(id) : "memory"); }

__device__ __forceinline__ void tma_2d(uint32_t dst, const CUtensorMap* tm, int c0, int c1, uint32_t bar) {
  asm volatile("cp.async.bulk.tensor.2d.shared::cluster.global.mbarrier::complete_tx::bytes [%0], [%1, {%3, %4}], [%2];"
               ::"r"(dst), "l"(tm), "r"(bar), "r"(c0), "r"(c1) : "memory");
}
__device__ __forceinline__ void tma_3d(uint32_t dst, const CUtensorMap* tm, int c0, int c1, int c2, uint32_t bar) {
  asm volatile("cp.async.bulk.tensor.3d.shared::cluster.global.mbarrier::complete_tx::bytes [%0], [%1, {%3, %4, %5}], [%2];"
               ::"r"(dst), "l"(tm), "r"(bar), "r"(c0), "r"(c1), "r"(c2) : "memory");
}
__device__ __forceinline__ void bulk_load(uint32_t dst, const void* src, uint32_t bytes, uint32_t bar) {
  asm volatile("cp.async.bulk.shared::cluster.global.mbarrier::complete_tx::bytes [%0], [%1], %2, [%3];"
               ::"r"(dst), "l"(src), "r"(bytes), "r"(bar) : "memory");
}
__device__ __forceinline__ void bulk_store(void* dst, uint32_t src, uint32_t bytes) {
  asm volatile("cp.async.bulk.global.shared::cta.bulk_group [%0], [%1], %2;" ::"l"(dst), "r"(src), "r"(bytes) : "memory");
}
__device__ __forceinline__ void bulk_wait_read() {
  asm volatile("cp.async.bulk.commit_group;\ncp.async.bulk.wait_group.read 0;" ::: "memory");
}

__device__ __forceinline__ void publish(void* dst, uint32_t src, uint32_t bytes) {
  bulk_store(dst, src, bytes);
  bulk_wait_read();
}

__device__ __forceinline__ void wg_fence() { asm volatile("wgmma.fence.sync.aligned;" ::: "memory"); }
__device__ __forceinline__ void wg_commit() { asm volatile("wgmma.commit_group.sync.aligned;" ::: "memory"); }
template <int N> __device__ __forceinline__ void wg_wait() { asm volatile("wgmma.wait_group.sync.aligned %0;" ::"n"(N) : "memory"); }
__device__ __forceinline__ uint32_t desc_lo(uint32_t addr, uint32_t lbo) { return ((addr & 0x3FFFF) >> 4) | ((lbo >> 4) << 16); }
constexpr uint32_t desc_hi(uint32_t sbo, uint32_t swz) { return (sbo >> 4) | (swz << 30); }
constexpr uint32_t HI_SW128 = desc_hi(1024, 1), HI_SW64 = desc_hi(512, 2), HI_SW32 = desc_hi(256, 3), HI_NONE = desc_hi(128, 0);
template <int N> __device__ __forceinline__ void pin(float* d) {
#pragma unroll
  for (int i = 0; i < N; i++) asm volatile("" : "+f"(d[i])::"memory");
}

__device__ __forceinline__ uint32_t lds32(uint32_t a) {
  uint32_t v;
  asm volatile("ld.volatile.shared.u32 %0, [%1];" : "=r"(v) : "r"(a) : "memory");
  return v;
}
__device__ __forceinline__ uint2 ldg64(const void* a) {
  uint2 v;
  asm volatile("ld.global.nc.v2.u32 {%0, %1}, [%2];" : "=r"(v.x), "=r"(v.y) : "l"(a) : "memory");
  return v;
}
__device__ __forceinline__ void ldsm4(uint32_t* r, uint32_t a) {
  asm volatile("ldmatrix.sync.aligned.m8n8.x4.shared.b16 {%0, %1, %2, %3}, [%4];"
               : "=r"(r[0]), "=r"(r[1]), "=r"(r[2]), "=r"(r[3]) : "r"(a) : "memory");
}
__device__ __forceinline__ void ldsm4t(uint32_t* r, uint32_t a) {
  asm volatile("ldmatrix.sync.aligned.m8n8.x4.trans.shared.b16 {%0, %1, %2, %3}, [%4];"
               : "=r"(r[0]), "=r"(r[1]), "=r"(r[2]), "=r"(r[3]) : "r"(a) : "memory");
}
__device__ __forceinline__ uint2 lds64(uint32_t a) {
  uint2 v;
  asm volatile("ld.shared.v2.u32 {%0, %1}, [%2];" : "=r"(v.x), "=r"(v.y) : "r"(a) : "memory");
  return v;
}
__device__ __forceinline__ uint4 lds128(uint32_t a) {
  uint4 v;
  asm volatile("ld.shared.v4.u32 {%0, %1, %2, %3}, [%4];" : "=r"(v.x), "=r"(v.y), "=r"(v.z), "=r"(v.w) : "r"(a) : "memory");
  return v;
}
__device__ __forceinline__ void sts128(uint32_t a, uint32_t x, uint32_t y, uint32_t z, uint32_t w) {
  asm volatile("st.shared.v4.u32 [%0], {%1, %2, %3, %4};" ::"r"(a), "r"(x), "r"(y), "r"(z), "r"(w) : "memory");
}
__device__ __forceinline__ void stsm4(uint32_t a, const uint32_t* r) {
  asm volatile("stmatrix.sync.aligned.m8n8.x4.shared.b16 [%0], {%1, %2, %3, %4};" ::"r"(a), "r"(r[0]), "r"(r[1]), "r"(r[2]), "r"(r[3]) : "memory");
}
__device__ __forceinline__ uint32_t pack2(float lo, float hi) {
  uint32_t r;
  asm("cvt.rn.bf16x2.f32 %0, %1, %2;" : "=r"(r) : "f"(hi), "f"(lo));
  return r;
}
__device__ __forceinline__ uint32_t movm(uint32_t a) {
  uint32_t d;
  asm volatile("movmatrix.sync.aligned.m8n8.trans.b16 %0, %1;" : "=r"(d) : "r"(a));
  return d;
}
__device__ __forceinline__ uint32_t bmul(uint32_t a, uint32_t b) {
  uint32_t d;
  asm("mul.rn.bf16x2 %0, %1, %2;" : "=r"(d) : "r"(a), "r"(b));
  return d;
}
__device__ __forceinline__ uint32_t badd(uint32_t a, uint32_t b) {
  uint32_t d;
  asm("add.rn.bf16x2 %0, %1, %2;" : "=r"(d) : "r"(a), "r"(b));
  return d;
}
__device__ __forceinline__ uint32_t bfma(uint32_t a, uint32_t b, uint32_t c) {
  uint32_t d;
  asm("fma.rn.bf16x2 %0, %1, %2, %3;" : "=r"(d) : "r"(a), "r"(b), "r"(c));
  return d;
}
__device__ __forceinline__ float bf_lo(uint32_t x) { return __uint_as_float(x << 16); }
__device__ __forceinline__ float bf_hi(uint32_t x) { return __uint_as_float(x & 0xFFFF0000u); }
__device__ __forceinline__ float ex2(float x) {
  float y;
  asm("ex2.approx.ftz.f32 %0, %1;" : "=f"(y) : "f"(x));
  return y;
}
__device__ __forceinline__ float rcp(float x) {
  float y;
  asm("rcp.approx.ftz.f32 %0, %1;" : "=f"(y) : "f"(x));
  return y;
}
__device__ __forceinline__ void mma16816(float* d, uint32_t a0, uint32_t a1, uint32_t a2, uint32_t a3, uint32_t b0, uint32_t b1) {
  asm volatile("mma.sync.aligned.m16n8k16.row.col.f32.bf16.bf16.f32 {%0, %1, %2, %3}, {%4, %5, %6, %7}, {%8, %9}, {%0, %1, %2, %3};"
               : "+f"(d[0]), "+f"(d[1]), "+f"(d[2]), "+f"(d[3])
               : "r"(a0), "r"(a1), "r"(a2), "r"(a3), "r"(b0), "r"(b1));
}
__device__ __forceinline__ void mma1688(float* d, uint32_t a0, uint32_t a1, uint32_t b0) {
  asm volatile("mma.sync.aligned.m16n8k8.row.col.f32.bf16.bf16.f32 {%0, %1, %2, %3}, {%4, %5}, {%6}, {%0, %1, %2, %3};"
               : "+f"(d[0]), "+f"(d[1]), "+f"(d[2]), "+f"(d[3])
               : "r"(a0), "r"(a1), "r"(b0));
}

template <int N> struct WgRS;
template <int N> struct WgSST;
template <> struct WgRS<32> {
  template <uint32_t HB>
  static __device__ __forceinline__ void mma(float* d, const uint32_t* a, uint32_t db) {
    asm volatile("{\n.reg .pred p;\n.reg .b64 db;\nsetp.ne.b32 p, %22, 0;\n"
      "mov.b64 db, {%20, %21};\n"
      "wgmma.mma_async.sync.aligned.m64n32k16.f32.bf16.bf16 {"
      "%0, %1, %2, %3, %4, %5, %6, %7, %8, %9, %10, %11, %12, %13, %14, %15"
      "}, {%16, %17, %18, %19}, db, p, 1, 1, 1;\n}\n"
      : "+f"(d[0]), "+f"(d[1]), "+f"(d[2]), "+f"(d[3]), "+f"(d[4]), "+f"(d[5]), "+f"(d[6]), "+f"(d[7]),
        "+f"(d[8]), "+f"(d[9]), "+f"(d[10]), "+f"(d[11]), "+f"(d[12]), "+f"(d[13]), "+f"(d[14]), "+f"(d[15])
      : "r"(a[0]), "r"(a[1]), "r"(a[2]), "r"(a[3]), "r"(db), "n"(HB), "n"(1));
  }
  template <uint32_t HB>
  static __device__ __forceinline__ void set(float* d, const uint32_t* a, uint32_t db) {
    asm volatile("{\n.reg .pred p;\n.reg .b64 db;\nsetp.ne.b32 p, %22, 0;\n"
      "mov.b64 db, {%20, %21};\n"
      "wgmma.mma_async.sync.aligned.m64n32k16.f32.bf16.bf16 {"
      "%0, %1, %2, %3, %4, %5, %6, %7, %8, %9, %10, %11, %12, %13, %14, %15"
      "}, {%16, %17, %18, %19}, db, p, 1, 1, 1;\n}\n"
      : "=f"(d[0]), "=f"(d[1]), "=f"(d[2]), "=f"(d[3]), "=f"(d[4]), "=f"(d[5]), "=f"(d[6]), "=f"(d[7]),
        "=f"(d[8]), "=f"(d[9]), "=f"(d[10]), "=f"(d[11]), "=f"(d[12]), "=f"(d[13]), "=f"(d[14]), "=f"(d[15])
      : "r"(a[0]), "r"(a[1]), "r"(a[2]), "r"(a[3]), "r"(db), "n"(HB), "n"(0));
  }
};
template <> struct WgRS<64> {
  template <uint32_t HB>
  static __device__ __forceinline__ void mma(float* d, const uint32_t* a, uint32_t db) {
    asm volatile("{\n.reg .pred p;\n.reg .b64 db;\nsetp.ne.b32 p, %38, 0;\n"
      "mov.b64 db, {%36, %37};\n"
      "wgmma.mma_async.sync.aligned.m64n64k16.f32.bf16.bf16 {"
      "%0, %1, %2, %3, %4, %5, %6, %7, %8, %9, %10, %11, %12, %13, %14, %15, "
      "%16, %17, %18, %19, %20, %21, %22, %23, %24, %25, %26, %27, %28, %29, %30, %31"
      "}, {%32, %33, %34, %35}, db, p, 1, 1, 1;\n}\n"
      : "+f"(d[0]), "+f"(d[1]), "+f"(d[2]), "+f"(d[3]), "+f"(d[4]), "+f"(d[5]), "+f"(d[6]), "+f"(d[7]),
        "+f"(d[8]), "+f"(d[9]), "+f"(d[10]), "+f"(d[11]), "+f"(d[12]), "+f"(d[13]), "+f"(d[14]), "+f"(d[15]),
        "+f"(d[16]), "+f"(d[17]), "+f"(d[18]), "+f"(d[19]), "+f"(d[20]), "+f"(d[21]), "+f"(d[22]), "+f"(d[23]),
        "+f"(d[24]), "+f"(d[25]), "+f"(d[26]), "+f"(d[27]), "+f"(d[28]), "+f"(d[29]), "+f"(d[30]), "+f"(d[31])
      : "r"(a[0]), "r"(a[1]), "r"(a[2]), "r"(a[3]), "r"(db), "n"(HB), "n"(1));
  }
  template <uint32_t HB>
  static __device__ __forceinline__ void set(float* d, const uint32_t* a, uint32_t db) {
    asm volatile("{\n.reg .pred p;\n.reg .b64 db;\nsetp.ne.b32 p, %38, 0;\n"
      "mov.b64 db, {%36, %37};\n"
      "wgmma.mma_async.sync.aligned.m64n64k16.f32.bf16.bf16 {"
      "%0, %1, %2, %3, %4, %5, %6, %7, %8, %9, %10, %11, %12, %13, %14, %15, "
      "%16, %17, %18, %19, %20, %21, %22, %23, %24, %25, %26, %27, %28, %29, %30, %31"
      "}, {%32, %33, %34, %35}, db, p, 1, 1, 1;\n}\n"
      : "=f"(d[0]), "=f"(d[1]), "=f"(d[2]), "=f"(d[3]), "=f"(d[4]), "=f"(d[5]), "=f"(d[6]), "=f"(d[7]),
        "=f"(d[8]), "=f"(d[9]), "=f"(d[10]), "=f"(d[11]), "=f"(d[12]), "=f"(d[13]), "=f"(d[14]), "=f"(d[15]),
        "=f"(d[16]), "=f"(d[17]), "=f"(d[18]), "=f"(d[19]), "=f"(d[20]), "=f"(d[21]), "=f"(d[22]), "=f"(d[23]),
        "=f"(d[24]), "=f"(d[25]), "=f"(d[26]), "=f"(d[27]), "=f"(d[28]), "=f"(d[29]), "=f"(d[30]), "=f"(d[31])
      : "r"(a[0]), "r"(a[1]), "r"(a[2]), "r"(a[3]), "r"(db), "n"(HB), "n"(0));
  }
};
template <> struct WgSST<48> {
  template <uint32_t HA, uint32_t HB>
  static __device__ __forceinline__ void mma(float* d, uint32_t da, uint32_t db, int sc) {
    asm volatile("{\n.reg .pred p;\n.reg .b64 da, db;\nsetp.ne.b32 p, %28, 0;\n"
      "mov.b64 da, {%24, %25};\nmov.b64 db, {%26, %27};\n"
      "wgmma.mma_async.sync.aligned.m64n48k16.f32.bf16.bf16 {"
      "%0, %1, %2, %3, %4, %5, %6, %7, %8, %9, %10, %11, %12, %13, %14, %15, "
      "%16, %17, %18, %19, %20, %21, %22, %23"
      "}, da, db, p, 1, 1, 0, 1;\n}\n"
      : "+f"(d[0]), "+f"(d[1]), "+f"(d[2]), "+f"(d[3]), "+f"(d[4]), "+f"(d[5]), "+f"(d[6]), "+f"(d[7]),
        "+f"(d[8]), "+f"(d[9]), "+f"(d[10]), "+f"(d[11]), "+f"(d[12]), "+f"(d[13]), "+f"(d[14]), "+f"(d[15]),
        "+f"(d[16]), "+f"(d[17]), "+f"(d[18]), "+f"(d[19]), "+f"(d[20]), "+f"(d[21]), "+f"(d[22]), "+f"(d[23])
      : "r"(da), "n"(HA), "r"(db), "n"(HB), "r"(sc));
  }
};
template <> struct WgSST<80> {
  template <uint32_t HA, uint32_t HB>
  static __device__ __forceinline__ void mma(float* d, uint32_t da, uint32_t db, int sc) {
    asm volatile("{\n.reg .pred p;\n.reg .b64 da, db;\nsetp.ne.b32 p, %44, 0;\n"
      "mov.b64 da, {%40, %41};\nmov.b64 db, {%42, %43};\n"
      "wgmma.mma_async.sync.aligned.m64n80k16.f32.bf16.bf16 {"
      "%0, %1, %2, %3, %4, %5, %6, %7, %8, %9, %10, %11, %12, %13, %14, %15, "
      "%16, %17, %18, %19, %20, %21, %22, %23, %24, %25, %26, %27, %28, %29, %30, %31, "
      "%32, %33, %34, %35, %36, %37, %38, %39"
      "}, da, db, p, 1, 1, 0, 1;\n}\n"
      : "+f"(d[0]), "+f"(d[1]), "+f"(d[2]), "+f"(d[3]), "+f"(d[4]), "+f"(d[5]), "+f"(d[6]), "+f"(d[7]),
        "+f"(d[8]), "+f"(d[9]), "+f"(d[10]), "+f"(d[11]), "+f"(d[12]), "+f"(d[13]), "+f"(d[14]), "+f"(d[15]),
        "+f"(d[16]), "+f"(d[17]), "+f"(d[18]), "+f"(d[19]), "+f"(d[20]), "+f"(d[21]), "+f"(d[22]), "+f"(d[23]),
        "+f"(d[24]), "+f"(d[25]), "+f"(d[26]), "+f"(d[27]), "+f"(d[28]), "+f"(d[29]), "+f"(d[30]), "+f"(d[31]),
        "+f"(d[32]), "+f"(d[33]), "+f"(d[34]), "+f"(d[35]), "+f"(d[36]), "+f"(d[37]), "+f"(d[38]), "+f"(d[39])
      : "r"(da), "n"(HA), "r"(db), "n"(HB), "r"(sc));
  }
};
template <> struct WgSST<192> {
  template <uint32_t HA, uint32_t HB>
  static __device__ __forceinline__ void mma(float* d, uint32_t da, uint32_t db, int sc) {
    asm volatile("{\n.reg .pred p;\n.reg .b64 da, db;\nsetp.ne.b32 p, %100, 0;\n"
      "mov.b64 da, {%96, %97};\nmov.b64 db, {%98, %99};\n"
      "wgmma.mma_async.sync.aligned.m64n192k16.f32.bf16.bf16 {"
      "%0, %1, %2, %3, %4, %5, %6, %7, %8, %9, %10, %11, %12, %13, %14, %15, "
      "%16, %17, %18, %19, %20, %21, %22, %23, %24, %25, %26, %27, %28, %29, %30, %31, "
      "%32, %33, %34, %35, %36, %37, %38, %39, %40, %41, %42, %43, %44, %45, %46, %47, "
      "%48, %49, %50, %51, %52, %53, %54, %55, %56, %57, %58, %59, %60, %61, %62, %63, "
      "%64, %65, %66, %67, %68, %69, %70, %71, %72, %73, %74, %75, %76, %77, %78, %79, "
      "%80, %81, %82, %83, %84, %85, %86, %87, %88, %89, %90, %91, %92, %93, %94, %95"
      "}, da, db, p, 1, 1, 0, 1;\n}\n"
      : "+f"(d[0]), "+f"(d[1]), "+f"(d[2]), "+f"(d[3]), "+f"(d[4]), "+f"(d[5]), "+f"(d[6]), "+f"(d[7]),
        "+f"(d[8]), "+f"(d[9]), "+f"(d[10]), "+f"(d[11]), "+f"(d[12]), "+f"(d[13]), "+f"(d[14]), "+f"(d[15]),
        "+f"(d[16]), "+f"(d[17]), "+f"(d[18]), "+f"(d[19]), "+f"(d[20]), "+f"(d[21]), "+f"(d[22]), "+f"(d[23]),
        "+f"(d[24]), "+f"(d[25]), "+f"(d[26]), "+f"(d[27]), "+f"(d[28]), "+f"(d[29]), "+f"(d[30]), "+f"(d[31]),
        "+f"(d[32]), "+f"(d[33]), "+f"(d[34]), "+f"(d[35]), "+f"(d[36]), "+f"(d[37]), "+f"(d[38]), "+f"(d[39]),
        "+f"(d[40]), "+f"(d[41]), "+f"(d[42]), "+f"(d[43]), "+f"(d[44]), "+f"(d[45]), "+f"(d[46]), "+f"(d[47]),
        "+f"(d[48]), "+f"(d[49]), "+f"(d[50]), "+f"(d[51]), "+f"(d[52]), "+f"(d[53]), "+f"(d[54]), "+f"(d[55]),
        "+f"(d[56]), "+f"(d[57]), "+f"(d[58]), "+f"(d[59]), "+f"(d[60]), "+f"(d[61]), "+f"(d[62]), "+f"(d[63]),
        "+f"(d[64]), "+f"(d[65]), "+f"(d[66]), "+f"(d[67]), "+f"(d[68]), "+f"(d[69]), "+f"(d[70]), "+f"(d[71]),
        "+f"(d[72]), "+f"(d[73]), "+f"(d[74]), "+f"(d[75]), "+f"(d[76]), "+f"(d[77]), "+f"(d[78]), "+f"(d[79]),
        "+f"(d[80]), "+f"(d[81]), "+f"(d[82]), "+f"(d[83]), "+f"(d[84]), "+f"(d[85]), "+f"(d[86]), "+f"(d[87]),
        "+f"(d[88]), "+f"(d[89]), "+f"(d[90]), "+f"(d[91]), "+f"(d[92]), "+f"(d[93]), "+f"(d[94]), "+f"(d[95])
      : "r"(da), "n"(HA), "r"(db), "n"(HB), "r"(sc));
  }
};

struct FftConst {
  uint32_t f[2][4], fi[4][4];
  uint32_t ta[2][2], tb[2][2];
};
__device__ __forceinline__ void cis(int m, float scale, float& c, float& s) {
  const float a = (float)m * (-6.283185307179586f * scale);
  c = __cosf(a);
  s = __sinf(a);
}
__device__ __forceinline__ void fft_tables(uint32_t (&v)[12], int tw) {
  const int row = tw >> 2, ch = tw & 3;
#pragma unroll
  for (int i = 0; i < 4; i++) {
    float c[2], s[2], x[2];
#pragma unroll
    for (int e = 0; e < 2; e++) {
      cis((((32 * (8 * ch + 2 * i + e) + 15) * (4 * row - 63) + 2048) & 4095) - 2048, 1.f / 4096, c[e], s[e]);
      float gc, gs;
      cis((((row & 15) * (8 * (ch & 1) + 2 * i + e) + 8) & 15) - 8, 1.f / 16, gc, gs);
      x[e] = (row >> 4) == (ch >> 1) ? gc : (ch >> 1) ? gs : -gs;
    }
    v[i] = pack2(c[0] * 0.125f, c[1] * 0.125f);
    v[4 + i] = pack2(s[0] * 0.125f, s[1] * 0.125f);
    v[8 + i] = pack2(x[0], x[1]);
  }
#pragma unroll
  for (int i = 0; i < 12; i++) asm volatile("" : "+r"(v[i]));
}
__device__ __forceinline__ void fft_tables_store(const uint32_t (&v)[12], uint32_t sb, int tw) {
  const int row = tw >> 2;
  const uint32_t x = ((tw ^ (row >> 1)) & 3) << 4, a = sb + OFF_FT + (16 * (row >> 3) + (row & 7)) * 64 + x;
  sts128(a, v[0], v[1], v[2], v[3]);
  sts128(a + 512, v[4], v[5], v[6], v[7]);
  sts128(sb + OFF_GT + row * 64 + x, v[8], v[9], v[10], v[11]);
}
__device__ __forceinline__ void fft_twiddles(uint32_t (&v)[2], int tw) {
  float a[2], s[2];
#pragma unroll
  for (int i = 0; i < 2; i++) {
    float c;
    cis((2 * (2 * (tw & 3) + i) - 15) * (4 * (tw >> 2) - 63), 1.f / 4096, c, s[i]);
    a[i] = __fdividef(-s[i], 1.f + c);
  }
  v[0] = pack2(a[0], a[1]);
  v[1] = pack2(s[0], s[1]);
  asm volatile("" : "+r"(v[0]), "+r"(v[1]));
}
__device__ __forceinline__ void fft_matrices(FftConst& k, uint32_t sb, int w, int lane) {
  const uint32_t x = (lane >> 1) & 3;
  const uint2 t0 = lds64(sb + OFF_TT + 256 * w + 8 * lane), t1 = lds64(sb + OFF_TT + 256 * w + 8 * (lane ^ 3));
  k.ta[0][0] = t0.x;
  k.tb[0][0] = t0.y;
  k.ta[1][1] = __byte_perm(t1.x, 0, 0x1032);
  k.tb[1][1] = __byte_perm(t1.y, 0, 0x1032);
#pragma unroll
  for (int j = 0; j < 2; j++) {
    k.ta[1 - j][j] = k.ta[j][j] ^ 0x80008000u;
    k.tb[1 - j][j] = k.tb[j][j] ^ 0x80008000u;
    asm volatile("" : "+r"(k.ta[0][j]), "+r"(k.tb[0][j]), "+r"(k.ta[1][j]), "+r"(k.tb[1][j]));
  }
#pragma unroll
  for (int i = 0; i < 2; i++) {
    ldsm4(k.f[i], sb + OFF_FT + (16 * w + (lane & 15)) * 64 + (((2 * i + (lane >> 4)) ^ x) << 4));
    ldsm4t(k.fi[i], sb + OFF_FT + (32 * i + lane) * 64 + ((w ^ x) << 4));
#pragma unroll
    for (int j = 0; j < 4; j++) {
      k.fi[2 + i][j] = (j & 1) ? k.fi[i][j - 1] ^ 0x80008000u : k.fi[i][j + 1];
      asm volatile("" : "+r"(k.fi[2 + i][j]));
    }
  }
}
__device__ __forceinline__ void rot(uint32_t& x, uint32_t& y, uint32_t a, uint32_t b) {
  x = bfma(a, y, x);
  y = bfma(b, x, y);
  x = bfma(a, y, x);
}
__device__ __forceinline__ void twiddle_fwd(uint32_t (&a)[4][4], float* d, const FftConst& k) {
#pragma unroll
  for (int q = 0; q < 4; q++)
#pragma unroll
    for (int j = 0; j < 2; j++) {
      const float* x = d + 8 * q + 4 * j;
      uint32_t re = pack2(x[0], x[1]), im = pack2(x[2], x[3]);
      rot(re, im, k.ta[0][j], k.tb[0][j]);
      a[q & 2][2 * j + (q & 1)] = re;
      a[(q & 2) + 1][2 * j + (q & 1)] = im;
    }
}
__device__ __forceinline__ void g_step(float* d, const uint32_t (&a)[4][4], uint32_t dre, uint32_t dim) {
  WgRS<32>::set<HI_SW64>(d, a[0], dre);
  WgRS<32>::set<HI_SW64>(d + 16, a[2], dre);
  WgRS<32>::mma<HI_SW64>(d, a[1], dim);
  WgRS<32>::mma<HI_SW64>(d + 16, a[3], dim);
  wg_commit();
}

__device__ __forceinline__ void products(uint32_t (&a)[4][4], const float* H, const float* U, int p) {
#pragma unroll
  for (int j = 0; j < 2; j++)
#pragma unroll
    for (int m = 2 * p; m < 2 * p + 2; m++) {
      float pr[2], pi[2];
#pragma unroll
      for (int x = 0; x < 2; x++)
#pragma unroll
        for (int q = 0; q <= m; q++) {
          const int ih = 16 * (q >> 1) + 2 * (q & 1) + 4 * j + x, iu = 16 * ((m - q) >> 1) + 2 * ((m - q) & 1) + 4 * j + x;
          pr[x] = q ? fmaf(H[ih], U[iu], pr[x]) : H[ih] * U[iu];
          pi[x] = q ? fmaf(H[ih], U[iu + 8], pi[x]) : H[ih] * U[iu + 8];
          pr[x] = fmaf(-H[ih + 8], U[iu + 8], pr[x]);
          pi[x] = fmaf(H[ih + 8], U[iu], pi[x]);
        }
      a[m & 2][2 * j + (m & 1)] = pack2(pr[0], pr[1]);
      a[(m & 2) + 1][2 * j + (m & 1)] = pack2(pi[0], pi[1]);
    }
}

__device__ __forceinline__ void filter_steps(const FftConst& k, uint32_t sb, int w, int lane) {
  float X[32];
  uint32_t a[4][4];
#pragma unroll 1
  for (uint32_t list = HLIST; list; list >>= 4) {
    const int c = (list & 7) - 1;
    const uint32_t hb = sb + off_ch(c) + U_BYTES, dh = desc_lo(hb, 1024);
    wg_fence();
    WgRS<64>::set<HI_SW32>(X, k.f[0], dh);
    WgRS<64>::mma<HI_SW32>(X, k.f[1], dh + 32);
    wg_commit();
    wg_wait<0>();
    pin<32>(X);
    wg_sync(3);
    twiddle_fwd(a, X, k);
#pragma unroll
    for (int j = 0; j < 4; j++) sts128(hb + 1024 * w + 16 * lane + 512 * (j & 1) + 4096 * (j >> 1), a[j][0], a[j][1], a[j][2], a[j][3]);
    __syncwarp();
    if (lane == 0) mbar_arrive(sb + OFF_BAR + 8 * (B_H + c));
    TSM(w == 0, 94 + c);
  }
}

__device__ __forceinline__ void conv_channel(const FftConst& k, uint32_t sb, int c, int wg, int w, int lane) {
  const uint32_t cb = sb + off_ch(c), bars = sb + OFF_BAR;
  const uint32_t du = desc_lo(cb, 1024), dg = desc_lo(sb + OFF_GT, 16), dz = desc_lo(cb + U_BYTES, 16);
  float U[32], H[32];
  uint32_t a[4][4], e[4][4];
  const float dv = __uint_as_float(lds32(sb + OFF_D + 4 * c));
  mbar_wait(bars + 8 * (B_H + c), 0);
#pragma unroll
  for (int j = 0; j < 4; j++) {
    const uint4 v = lds128(cb + U_BYTES + 1024 * w + 16 * lane + 512 * (j & 1) + 4096 * (j >> 1));
    a[j][0] = v.x; a[j][1] = v.y; a[j][2] = v.z; a[j][3] = v.w;
  }
  mbar_wait(bars + 8 * (B_U + (c < 3 ? c : 3)), 0);
  TSM(w == 0 && c < 3, 7 + wg);
  wg_fence();
  WgRS<64>::set<HI_SW32>(U, k.f[0], du);
  WgRS<64>::mma<HI_SW32>(U, k.f[1], du + 32);
  wg_commit();
  g_step(H, a, dg, dg + 64);
  wg_wait<1>();
  pin<32>(U);
  twiddle_fwd(e, U, k);
  wg_fence();
  g_step(U, e, dg, dg + 64);
  wg_wait<0>();
  pin<32>(U);
  pin<32>(H);
#pragma unroll
  for (int j = 0; j < 4; j++) H[4 * (j >> 1) + (j & 1)] += dv;
  float V[32];
#pragma unroll
  for (int p = 0; p < 2; p++) {
    products(a, H, U, p);
    wg_fence();
    WgRS<32>::set<HI_SW64>(V + 16 * p, a[2 * p], dg + 64);
    WgRS<32>::mma<HI_SW64>(V + 16 * p, a[2 * p + 1], dg);
    wg_commit();
  }
  const uint32_t za = cb + U_BYTES + (8 * w + (lane & 7)) * 128 + (((lane >> 3) ^ (lane & 7)) << 4);
  const uint32_t ya = cb + (lane >> 4) * 1024 + (8 * w + (lane & 7)) * 32 + ((((lane >> 3) ^ (lane >> 2)) & 1) << 4);
#pragma unroll
  for (int p = 0; p < 2; p++) {
    if (p == 0) wg_wait<1>();
    else wg_wait<0>();
    pin<16>(V + 16 * p);
#pragma unroll
    for (int i = 0; i < 4; i++) {
      const int j = i & 1;
      const float* x = V + 16 * p + 4 * j + (i & 2);
      e[p][i] = pack2(x[8], x[9]);
      e[2 + p][i] = pack2(x[0], x[1]);
      rot(e[p][i], e[2 + p][i], k.ta[1][j], k.tb[1][j]);
    }
    stsm4(za ^ (64 * p), e[p]);
    stsm4((za ^ (64 * p)) + 4096, e[2 + p]);
  }
  fence_async_smem();
  wg_sync(1 + wg);
  wg_fence();
  WgRS<64>::set<HI_SW128>(H, k.fi[0], dz);
#pragma unroll
  for (int ks = 1; ks < 4; ks++) WgRS<64>::mma<HI_SW128>(H, k.fi[ks], dz + 128 * ks);
  wg_commit();
  wg_wait<0>();
  pin<32>(H);
  if (lane == 0) mbar_arrive(bars + 8 * B_CVD);
  TSIF(w == 0, 88 + c);
#pragma unroll
  for (int j = 0; j < 8; j++)
    a[j >> 2][j & 3] = j < 2 ? pack2(H[4 * j], H[4 * j + 1]) : pack2(H[4 * j] + H[4 * j - 6], H[4 * j + 1] + H[4 * j - 5]);
  stsm4(ya, a[0]);
  stsm4(ya + 2048, a[1]);
  fence_async_smem();
  __syncwarp();
}

__device__ __forceinline__ void prep_slab(uint4* res, const uint2* sw, uint32_t sb, int slab, int w, int lane) {
  const int t = lane & 3, tp = (lane & 7) >> 1, pos = 8 * tp + 2 * (((lane >> 3) + tp) & 3) + (lane & 1);
  const uint32_t base = sb + OFF_KVS + slab * KVS_BYTES + pos * 128;
  uint32_t kk[2][4][4], vv[2][4];
  mbar_wait(sb + OFF_BAR + 8 * (B_KV + slab), 0);
#pragma unroll
  for (int h = 0; h < 2; h++) {
#pragma unroll
    for (int j = 0; j < 4; j++) {
      const uint32_t a = base + 128 * j;
      ldsm4t(kk[h][j], a + (((w + 4 * h) ^ ((a >> 7) & 7)) << 4));
    }
    const uint32_t a = base + KVS_V;
    ldsm4t(vv[h], a + (((w + 4 * h) ^ ((a >> 7) & 7)) << 4));
  }
#pragma unroll
  for (int h = 0; h < 2; h++) {
    uint32_t (&k)[4][4] = kk[h];
    uint32_t (&v)[4] = vv[h];
    const uint32_t w0 = __byte_perm(sw[h].x, 0, 0x1010), w1 = __byte_perm(sw[h].x, 0, 0x3232);
    const uint32_t w2 = __byte_perm(sw[h].y, 0, 0x1010), w3 = __byte_perm(sw[h].y, 0, 0x3232);
#pragma unroll
    for (int m = 0; m < 4; m++)
      v[m] = bmul(badd(badd(badd(bmul(k[0][m], w3), bmul(k[1][m], w2)), bmul(k[2][m], w1)), bmul(k[3][m], w0)), v[m]);
    uint32_t a[4];
#pragma unroll
    for (int m = 0; m < 4; m++) a[m] = (t & 1) ? v[(m + 3) & 3] : v[m];
    res[h] = (t & 2) ? make_uint4(a[2], a[3], a[0], a[1]) : make_uint4(a[0], a[1], a[2], a[3]);
  }
}

__device__ __forceinline__ void prep_gate(const Params& p, uint32_t sb, int b, int w, int lane) {
  uint2 gw[5], x[4][5];
#pragma unroll
  for (int j = 0; j < 5; j++) gw[j] = ldg64(reinterpret_cast<const uint2*>(p.gate_w) + lane + 32 * j);
#pragma unroll
  for (int i = 0; i < 4; i++)
#pragma unroll
    for (int j = 0; j < 5; j++)
      x[i][j] = ldg64(reinterpret_cast<const uint2*>(p.q) + (16 * b + 4 * w + i) * (DIM / 4) + lane + 32 * j);
  float s[4];
#pragma unroll
  for (int i = 0; i < 4; i++) {
    s[i] = 0.f;
#pragma unroll
    for (int j = 0; j < 5; j++) {
      const uint32_t m0 = bmul(x[i][j].x, gw[j].x), m1 = bmul(x[i][j].y, gw[j].y);
      s[i] += (bf_lo(m0) + bf_hi(m0)) + (bf_lo(m1) + bf_hi(m1));
    }
  }
  const bool h = lane & 16, q = lane & 8;
  const float a = (h ? s[2] : s[0]) + __shfl_xor_sync(0xffffffffu, h ? s[0] : s[2], 16);
  const float c = (h ? s[3] : s[1]) + __shfl_xor_sync(0xffffffffu, h ? s[1] : s[3], 16);
  float z = (q ? c : a) + __shfl_xor_sync(0xffffffffu, q ? a : c, 8);
#pragma unroll
  for (int o = 4; o > 0; o >>= 1) z += __shfl_xor_sync(0xffffffffu, z, o);
  z = bf_lo(pack2(z, 0.f));
  z = bf_lo(pack2(__fdividef(1.f, 1.f + __expf(-z)), 0.f));
  mbar_wait(sb + OFF_BAR + 8 * B_S3, 0);
  if ((lane & 7) == 0) asm volatile("st.shared.f32 [%0], %1;" ::"r"(sb + OFF_GATE + 64 * (b & 7) + 16 * w + (lane >> 1)), "f"(z) : "memory");
  fence_async_smem();
}

__device__ __forceinline__ uint32_t bmax(uint32_t a, uint32_t b) {
  uint32_t d;
  asm("max.bf16x2 %0, %1, %2;" : "=r"(d) : "r"(a), "r"(b));
  return d;
}
__device__ __forceinline__ void softmax_two(const float (&l)[2][2], uint32_t& p0, uint32_t& p1) {
  constexpr float kScale = 0.22360679774997896f, kLog2e = 1.4426950408889634f;
  const uint32_t r0 = pack2(l[0][0], l[1][0]), r1 = pack2(l[0][1], l[1][1]);
  const uint32_t x0 = pack2(bf_lo(r0) * kScale, bf_hi(r0) * kScale), x1 = pack2(bf_lo(r1) * kScale, bf_hi(r1) * kScale);
  uint32_t m = bmax(x0, x1);
  m = bmax(m, __shfl_xor_sync(0xffffffffu, m, 1));
  m = bmax(m, __shfl_xor_sync(0xffffffffu, m, 2));
  const float m0 = bf_lo(m) * kLog2e, m1 = bf_hi(m) * kLog2e;
  p0 = pack2(ex2(bf_lo(x0) * kLog2e - m0), ex2(bf_lo(x1) * kLog2e - m0));
  p1 = pack2(ex2(bf_hi(x0) * kLog2e - m1), ex2(bf_hi(x1) * kLog2e - m1));
}

__device__ __forceinline__ void halo_read(uint32_t (&kpv)[10], uint32_t (&vpv)[10], uint32_t (&tg)[7], const uint4* hp) {
#pragma unroll
  for (int j = 0; j < 7; j++) {
    uint32_t x0, x1, x2;
    asm volatile("ld.relaxed.gpu.global.v4.u32 {%0, %1, %2, %3}, [%4];"
                 : "=r"(x0), "=r"(x1), "=r"(x2), "=r"(tg[j]) : "l"(hp + 32 * j) : "memory");
    if (j < 4) kpv[3 * j] = x0; else vpv[3 * j - 10] = x0;
    if (j < 3) kpv[3 * j + 1] = x1; else vpv[3 * j - 9] = x1;
    if (j < 3) kpv[3 * j + 2] = x2; else if (j < 6) vpv[3 * j - 8] = x2;
  }
}

template <int ROT>
__device__ __forceinline__ void pack_qkv(const float* acc, uint32_t (&qlo)[10], uint32_t (&qhi)[10], uint32_t (&klo)[10],
                                         uint32_t (&khi)[10], uint32_t (&vlo)[10], uint32_t (&vhi)[10]) {
#pragma unroll
  for (int j = 0; j < 10; j++) {
    const int x = (j + ROT) % 10, tq = x < 8 ? x : 16 + x, tk = x < 8 ? 8 + x : 18 + x, tv = x < 8 ? 16 + x : 20 + x;
    khi[j] = pack2(acc[4 * tk + 2], acc[4 * tk + 3]);
    vhi[j] = movm(pack2(acc[4 * tv + 2], acc[4 * tv + 3]));
    qlo[j] = pack2(acc[4 * tq], acc[4 * tq + 1]);
    qhi[j] = pack2(acc[4 * tq + 2], acc[4 * tq + 3]);
    klo[j] = pack2(acc[4 * tk], acc[4 * tk + 1]);
    vlo[j] = pack2(acc[4 * tv], acc[4 * tv + 1]);
    asm volatile("" : "+r"(khi[j]), "+r"(qlo[j]), "+r"(qhi[j]), "+r"(klo[j]), "+r"(vlo[j]));
  }
}

template <int ROT> __device__ __forceinline__ void halo_send(const float* acc, uint4* ho, uint32_t tag) {
#pragma unroll
  for (int j = 0; j < 7; j++) {
    uint32_t x[3];
#pragma unroll
    for (int e = 0; e < 3; e++) {
      const int i = 3 * j + e, y = (i % 10 + ROT) % 10, tk = y < 8 ? 8 + y : 18 + y, tv = y < 8 ? 16 + y : 20 + y;
      x[e] = i < 10 ? pack2(acc[4 * tk + 2], acc[4 * tk + 3]) : i < 20 ? movm(pack2(acc[4 * tv + 2], acc[4 * tv + 3])) : 0u;
    }
    asm volatile("st.relaxed.gpu.global.v4.u32 [%0], {%1, %2, %3, %4};" ::"l"(ho + 32 * j), "r"(x[0]), "r"(x[1]), "r"(x[2]), "r"(tag) : "memory");
  }
}

__device__ __forceinline__ void attention(float* acc, uint32_t sb, int b, int par, int w, int lane, uint32_t tag) {
  const int g = lane >> 2, t = lane & 3;
  uint32_t klo[10], khi[10], vlo[10], vhi[10], qlo[10], qhi[10], kpv[10], vpv[10];
  if (w == 3 && b < NCTA - 8) {
    uint4* ho = g_halo + (b * 2 + par) * 224 + lane;
    if (tail_first(b & 7)) halo_send<8>(acc, ho, tag);
    else halo_send<0>(acc, ho, tag);
    TSIF(par == 0, 76);
    pin<120>(acc);
  }
  if (tail_first(b & 7)) pack_qkv<8>(acc, qlo, qhi, klo, khi, vlo, vhi);
  else pack_qkv<0>(acc, qlo, qhi, klo, khi, vlo, vhi);
  const uint32_t xa = sb + OFF_KVX + (par * 3) * 2560 + lane * 16;
  if (w < 3) {
    sts128(xa + w * 2560, khi[0], khi[1], khi[2], khi[3]);
    sts128(xa + w * 2560 + 512, khi[4], khi[5], khi[6], khi[7]);
    sts128(xa + w * 2560 + 1024, khi[8], khi[9], vhi[0], vhi[1]);
    sts128(xa + w * 2560 + 1536, vhi[2], vhi[3], vhi[4], vhi[5]);
    sts128(xa + w * 2560 + 2048, vhi[6], vhi[7], vhi[8], vhi[9]);
  }
  TSIF(par == 0 && w == 1, 64);
#pragma unroll
  for (int j = 0; j < 10; j++) vlo[j] = movm(vlo[j]);
  const bool far0 = 2 * t > g, far1 = 2 * t + 1 > g;
  const uint32_t mfar = (far0 ? 0x0000FFFFu : 0u) | (far1 ? 0xFFFF0000u : 0u);
  float slo[4][2], lg[2][2];
  uint32_t phi[4], plo[4], qml[4], qmh[4];
#pragma unroll
  for (int h = 0; h < 4; h++) {
    const int f = h == 0 ? 0 : h == 1 ? 3 : h == 2 ? 5 : 8, hf = h < 2 ? 2 : 7;
    const bool mine = (h & 1) ? t >= 2 : t < 2;
    qml[h] = mine ? qlo[hf] : 0u;
    qmh[h] = mine ? qhi[hf] : 0u;
    float a[4] = {0.f, 0.f, 0.f, 0.f}, c[4] = {0.f, 0.f, 0.f, 0.f};
    mma16816(a, qlo[f], qhi[f], qlo[f + 1], qhi[f + 1], klo[f], klo[f + 1]);
    mma16816(c, qlo[f], qhi[f], qlo[f + 1], qhi[f + 1], khi[f], khi[f + 1]);
    mma1688(a, qml[h], qmh[h], klo[hf]);
    mma1688(c, qml[h], qmh[h], khi[hf]);
    slo[h][0] = a[0];
    slo[h][1] = a[1];
    lg[h & 1][0] = far0 ? a[2] : c[2];
    lg[h & 1][1] = far1 ? a[3] : c[3];
    if (h & 1) softmax_two(lg, phi[h - 1], phi[h]);
  }
  TSIF(par == 0 && w == 1, 65);
  wg_sync(1 + par);
  TSIF(par == 0 && w == 1, 66);
  const bool nohist = (w == 0) && (b < 8);
  const uint4* hp = g_halo + ((b - 8) * 2 + par) * 224 + lane;
  uint32_t tg[7];
  if (w > 0) {
    const uint4 v0 = lds128(xa + (w - 1) * 2560), v1 = lds128(xa + (w - 1) * 2560 + 512), v2 = lds128(xa + (w - 1) * 2560 + 1024);
    const uint4 v3 = lds128(xa + (w - 1) * 2560 + 1536), v4 = lds128(xa + (w - 1) * 2560 + 2048);
    kpv[0] = v0.x; kpv[1] = v0.y; kpv[2] = v0.z; kpv[3] = v0.w; kpv[4] = v1.x; kpv[5] = v1.y; kpv[6] = v1.z; kpv[7] = v1.w;
    kpv[8] = v2.x; kpv[9] = v2.y; vpv[0] = v2.z; vpv[1] = v2.w; vpv[2] = v3.x; vpv[3] = v3.y; vpv[4] = v3.z; vpv[5] = v3.w;
    vpv[6] = v4.x; vpv[7] = v4.y; vpv[8] = v4.z; vpv[9] = v4.w;
  } else if (nohist) {
#pragma unroll
    for (int j = 0; j < 10; j++) kpv[j] = vpv[j] = 0u;
  } else {
    TSIF(par == 0, 77);
    halo_read(kpv, vpv, tg, hp);
  }
  if (w == 0 && !nohist) {
    int spins = 0;
    while (true) {
      bool ok = true;
#pragma unroll
      for (int j = 0; j < 7; j++) ok = ok && tg[j] == tag;
      if (__all_sync(0xffffffffu, ok) || ++spins > SPIN_LIMIT) break;
      halo_read(kpv, vpv, tg, hp);
    }
    TSIF(par == 0, 79);
  }
#pragma unroll
  for (int h = 0; h < 4; h++) {
    const int f = h == 0 ? 0 : h == 1 ? 3 : h == 2 ? 5 : 8, hf = h < 2 ? 2 : 7;
    float a[4] = {0.f, 0.f, 0.f, 0.f};
    mma16816(a, qlo[f], qhi[f], qlo[f + 1], qhi[f + 1], kpv[f], kpv[f + 1]);
    mma1688(a, qml[h], qmh[h], kpv[hf]);
    const float ninf = __int_as_float(0xff800000);
    lg[h & 1][0] = far0 ? (nohist ? ninf : a[0]) : slo[h][0];
    lg[h & 1][1] = far1 ? (nohist ? ninf : a[1]) : slo[h][1];
    if (h & 1) softmax_two(lg, plo[h - 1], plo[h]);
  }
  TSIF(par == 0 && w <= 1, 67 + w);
  uint32_t ov[20];
#pragma unroll
  for (int hp = 0; hp < 2; hp++) {
    const int hf = hp ? 7 : 2;
    float sh[4] = {0.f, 0.f, 0.f, 0.f}, i0 = 0.f, i1 = 0.f;
#pragma unroll
    for (int e = 0; e < 2; e++) {
      const int h = 2 * hp + e, f = h == 0 ? 0 : h == 1 ? 3 : h == 2 ? 5 : 8;
      const uint32_t a0 = plo[h] & mfar, a2 = plo[h] & ~mfar, a3 = phi[h] & mfar, c1 = phi[h] & ~mfar;
      float sum[4] = {0.f, 0.f, 0.f, 0.f};
      mma1688(sum, plo[h], phi[h], 0x3F803F80u);
      const float r0 = rcp(sum[0]), r1 = rcp(sum[2]);
#pragma unroll
      for (int j = f; j < f + 2; j++) {
        float o[4] = {0.f, 0.f, 0.f, 0.f};
        mma16816(o, a0, 0u, a2, a3, vpv[j], vlo[j]);
        mma1688(o, 0u, c1, vhi[j]);
        ov[2 * j] = pack2(o[0] * r0, o[1] * r0);
        ov[2 * j + 1] = pack2(o[2] * r1, o[3] * r1);
      }
      const bool mine = e ? g >= 4 : g < 4;
      mma16816(sh, a0, 0u, a2, a3, mine ? vpv[hf] : 0u, mine ? vlo[hf] : 0u);
      mma1688(sh, 0u, c1, mine ? vhi[hf] : 0u);
      if (e == 0 || t >= 2) {
        i0 = r0;
        i1 = r1;
      }
    }
    ov[2 * hf] = pack2(sh[0] * i0, sh[1] * i0);
    ov[2 * hf + 1] = pack2(sh[2] * i1, sh[3] * i1);
  }
  TS(32 + 4 * par + w);
  mbar_wait(sb + OFF_BAR + 8 * B_P1, 0);
  const uint32_t oa = sb + OFF_OA + (lane >> 4) * 2048 + (32 * w + 2 * (lane & 15) + par) * 16;
#pragma unroll
  for (int j = 0; j < 5; j++) stsm4(oa + 4096 * j, ov + 4 * j);
  TSIF(par == 0 && w == 0, 120);
  fence_async_smem();
  TSIF(par == 0 && w == 0, 121);
  __syncwarp();
  if (lane == 0) mbar_arrive(sb + OFF_BAR + 8 * B_ATTN);
  TSM(w == 0 || w == 2, 122 + par + (w == 2 ? 3 : 0));
}

struct Maps {
  CUtensorMap x, wm, wt, k, v, y, wo, qm, qt, om, ot, yl, ol;
};

__device__ __forceinline__ void load_stage(uint32_t sb, int kb, int b, const Maps& m) {
  const uint32_t st = sb + (kb & 3) * STAGE_BYTES, bar = sb + OFF_BAR + 8 * (B_FULL1 + (kb & 3));
  const int r = b >> 3, hg = b & 7, slab = kb - KV_KB;
  const bool kv = slab >= 0 && slab < 5;
  const uint32_t kbar = sb + OFF_BAR + 8 * (B_KV + slab), dst = sb + OFF_KVS + slab * KVS_BYTES;
  mbar_expect_tx(bar, STAGE_BYTES);
  if (kv) mbar_expect_tx(kbar, KVS_BYTES);
  tma_3d(st, &m.x, 64 * kb, 64 * r, 0, bar);
  tma_3d(st + ST_W, &m.wm, 80 * hg + (tail_first(hg) ? 16 : 0), 64 * kb, 0, bar);
  tma_3d(st + ST_WT, &m.wt, 80 * hg + (tail_first(hg) ? 0 : 64), 64 * kb, 0, bar);
  if (kv) tma_3d(dst, &m.k, 0, 32 * (b >> 1) - 3, 2 * slab + (b & 1), kbar);
  if (kv) tma_3d(dst + KVS_V, &m.v, 0, 32 * (b >> 1), 2 * slab + (b & 1), kbar);
}

__global__ void __launch_bounds__(NTHR, 1) fused_kernel(const __grid_constant__ Maps m, const Params p) {
  extern __shared__ __align__(1024) uint8_t smem[];
  const uint32_t sb = (uint32_t)__cvta_generic_to_shared(smem);
  const uint32_t bars = sb + OFF_BAR;
  const int tid = threadIdx.x, lane = tid & 31;
  int b = blockIdx.x;
  b = (((b & 63) >> 3) * 2 + (b & 1)) * 8 + (((b < 64 ? 0x6521 : 0x7430) >> (4 * ((b >> 1) & 3))) & 7);
  const int r = b >> 3, hg = b & 7;

  if (tid == T_ISSUE) {
    TSM(true, 0);
    mbar_init(bars + 8 * B_F0, 1);
    fence_async_smem();
    mbar_expect_tx(bars + 8 * B_F0, ST_WT);
    tma_3d(sb, &m.x, 0, 64 * r, 0, bars + 8 * B_F0);
    tma_3d(sb + ST_W, &m.wm, 80 * hg + (tail_first(hg) ? 16 : 0), 0, 0, bars + 8 * B_F0);
#pragma unroll
    for (int i = 0; i < 4; i++) mbar_init(bars + 8 * (B_FULL1 + i), 1);
    fence_async_smem();
    mbar_expect_tx(bars + 8 * B_FULL1, STAGE_BYTES - ST_WT);
    tma_3d(sb + ST_WT, &m.wt, 80 * hg + (tail_first(hg) ? 0 : 64), 0, 0, bars + 8 * B_FULL1);
    load_stage(sb, 1, b, m);
  } else if (tid == T_INIT) {
#pragma unroll
    for (int i = 0; i < B_F0; i++) mbar_init(bars + 8 * i, i < B_GATE ? 8 : i < B_CVD ? 4 : i == B_CVD ? 20 : 1);
    fence_async_smem();
  }
  const int warp = __shfl_sync(0xffffffffu, tid >> 5, 0), wg = warp >> 2, w = warp & 3;
  __syncthreads();

  if (wg == 3) {
    asm volatile("setmaxnreg.dec.sync.aligned.u32 56;");
    if (w == 0) {
      if (lane == 0) {
#pragma unroll 1
        for (int kb = 2; kb < 10; kb++) {
          if (kb >= 4) mbar_wait(bars + 8 * (kb == 7 ? B_E3 : B_EMPTY1 + (kb & 3)), (kb >> 3) & 1);
          TSIF(kb >= 4, 44 + kb);
          load_stage(sb, kb, b, m);
          TSIF(kb == 3, 60);
          if (kb == 9) mbar_arrive(bars + 8 * B_LAST);
        }
        mbar_wait(bars + 8 * B_WOP, 0);
        mbar_wait(bars + 8 * B_EPOCH, 0);
        flag_wait(g_cnt + C_W + 32 * hg, (lds32(sb + OFF_EPOCH) + 1) * 16);
        TS(30);
#pragma unroll 1
        for (int j = 0; j < 8; j++) {
          if (j >= 6) mbar_wait(bars + 8 * (B_EMPTY2 + j - 6), 0);
          if (j == 4) mbar_wait(bars + 8 * B_ORB, 0);
          TSIF(j >= 6, 100 + j);
          mbar_expect_tx(bars + 8 * (B_FULL2 + j), j == 0 ? WO_BYTES : j == 5 ? O_BYTES + WO_BYTES + 512 : O_BYTES + WO_BYTES);
          bulk_load(sb + off_w(j), g_WO + (hg * 8 + step_src(hg, j)) * 800, WO_BYTES, bars + 8 * (B_FULL2 + j));
        }
        mbar_wait(bars + 8 * (B_EMPTY2 + 3), 0);
        mbar_expect_tx(bars + 8 * B_QF, O_BYTES);
        tma_2d(sb + OFF_QS, &m.qm, 80 * hg, 128 * r, bars + 8 * B_QF);
        tma_2d(sb + OFF_QT, &m.qt, 80 * hg + 64, 128 * r, bars + 8 * B_QF);
      }
    } else if (w == 1) {
      unsigned epoch = 0;
      if (lane == 0) {
        epoch = atomicAdd(g_cnt + C_LAUNCH, 1u) / NCTA;
        asm volatile("st.shared.u32 [%0], %1;" ::"r"(sb + OFF_EPOCH), "r"(epoch) : "memory");
        mbar_arrive(bars + 8 * B_EPOCH);
        mbar_wait(bars + 8 * B_KVD, 0);
        mbar_expect_tx(bars + 8 * B_HB, 5 * 4096);
#pragma unroll 1
        for (int c = 0; c < 5; c++) {
          if (c == 3) mbar_wait(bars + 8 * B_S3, 0);
          bulk_load(sb + off_ch(c) + U_BYTES, p.ssm_k + (5 * b + c) * SEQ, 4096, bars + 8 * B_HB);
        }
#pragma unroll
        for (int c = 0; c < 4; c++) mbar_expect_tx(bars + 8 * (B_U + c), c < 3 ? U_BYTES : 2 * U_BYTES);
        const uint4* usrc = g_U + 5 * b * U_PITCH;
        mbar_wait(bars + 8 * B_USIG, 0);
        flag_wait(g_cnt + C_PREP + 32 * (b & 15), (epoch + 1) * NCTA);
        TS(23);
#pragma unroll
        for (int c = 0; c < 5; c++) {
          if (c == 3) mbar_wait(bars + 8 * (B_U + 2), 0);
          bulk_load(sb + off_ch(c), usrc + c * U_PITCH, U_BYTES, bars + 8 * (B_U + (c < 3 ? c : 3)));
          TSIF(c == 0 || c == 4, 116 + (c >> 2));
        }
      }
      epoch = __shfl_sync(0xffffffffu, epoch, 0);
      if (lane < 8) {
        const int src = (b & ~7) | step_src(hg, lane);
        mbar_wait(bars + 8 * B_ATTN, 0);
        TS(20);
        bool seen = false;
#pragma unroll 1
        for (int spins = 0; spins < SPIN_LIMIT; spins++) {
          const bool now = !seen && (int)(flag_read(g_cnt + C_O + 32 * src) - (epoch + 1)) >= 0;
          if (now && lane >= 1 && lane < 4) bulk_load(sb + off_o(lane), g_O + src * 1280, O_BYTES, bars + 8 * (B_FULL2 + lane));
          seen = seen || now;
          if (__all_sync(0xff, seen)) break;
        }
        TS(21);
        if (lane == 5) bulk_load(sb + OFF_GATE, g_gate + 128 * r, 512, bars + 8 * (B_FULL2 + 5));
#pragma unroll 1
        for (int j = 4; j < 8; j++) {
          if (lane == j) {
            mbar_wait(bars + 8 * (j < 6 ? B_C34 : B_EMPTY2 + j - 6), 0);
            bulk_load(sb + off_o(j), g_O + src * 1280, O_BYTES, bars + 8 * (B_FULL2 + j));
          }
          __syncwarp(0xff);
        }
        TS(22);
      }
    } else if (w == 2) {
      mbar_wait(bars + 8 * B_PREP, 0);
      flag_signal(g_cnt + C_PREP, 16, lane);
      TS(25);
      if (lane == 0) {
        mbar_arrive(bars + 8 * B_USIG);
        mbar_expect_tx(bars + 8 * B_ORB, O_BYTES / 4 + 64);
        mbar_wait(bars + 8 * B_GATE, 0);
        publish(g_gate + 16 * b, sb + OFF_GATE + 64 * hg, 64);
        bulk_load(sb + OFF_GATE + 64 * hg, g_gate + 16 * b, 64, bars + 8 * B_ORB);
        mbar_wait(bars + 8 * B_ATTN, 0);
        publish(g_O + b * 1280, sb + OFF_OA, O_BYTES);
        tma_2d(sb + OFF_KVX + 10240, &m.ol, 48, b * 160, bars + 8 * B_ORB);
        TS(74);
        mbar_wait(bars + 8 * B_ORB, 0);
        flag_bump(g_cnt + C_O + 32 * b);
        TS(26);
      }
    } else {
      if (lane == 0) {
        uint4* dst = g_WO + (hg * 8 + (r >> 1)) * 800 + (r & 1) * 80;
        mbar_wait(bars + 8 * B_S3, 0);
        asm volatile("cp.async.bulk.prefetch.L2.global [%0], 6400;" ::"l"(p.wo + b * 3200) : "memory");
        mbar_wait(bars + 8 * B_P1, 0);
        mbar_wait(bars + 8 * WB_TRIG, 0);
        mbar_expect_tx(bars + 8 * B_WST, WO_BYTES / 2);
        tma_3d(sb + OFF_WA, &m.wo, 0, 40 * r, 5 * hg, bars + 8 * B_WST);
        mbar_wait(bars + 8 * B_WST, 0);
#pragma unroll 1
        for (int n = 0; n < 5; n++) bulk_store(dst + 160 * n, sb + OFF_WA + 1280 * n, 1280);
        bulk_wait_read();
        mbar_expect_tx(bars + 8 * B_WST, WO_BYTES / 2);
#pragma unroll 1
        for (int n = 0; n < 5; n++) bulk_load(sb + OFF_WA + 1280 * n, dst + 160 * n, 1280, bars + 8 * B_WST);
        mbar_wait(bars + 8 * B_WST, 1);
        flag_bump(g_cnt + C_W + 32 * hg);
        mbar_arrive(bars + 8 * B_WOP);
        TS(71);
        mbar_expect_tx(bars + 8 * B_C34, 3 * (U_BYTES / 4));
        mbar_expect_tx(bars + 8 * B_YRB, 2 * (U_BYTES / 4));
#pragma unroll 1
        for (int c = 0; c < 5; c++) {
          mbar_wait(bars + 8 * (B_YST + c), 0);
          publish(g_U + (5 * b + c) * U_PITCH, sb + off_ch(c), U_BYTES);
          tma_2d(sb + off_ch(c), &m.yl, 48, (5 * b + c) * (U_PITCH / 8), bars + 8 * (c < 3 ? B_C34 : B_YRB));
        }
        TS(75);
        mbar_wait(bars + 8 * B_C34, 0);
        mbar_wait(bars + 8 * B_YRB, 0);
        flag_bump(g_cnt + C_Y + 32 * (b >> 4));
        TS(27);
        mbar_expect_tx(bars + 8 * B_YFULL, 20480);
        flag_wait(g_cnt + C_Y + 32 * hg, (lds32(sb + OFF_EPOCH) + 1) * 16);
        TS(24);
        tma_2d(sb + OFF_YT, &m.y, 128 * r, 80 * hg, bars + 8 * B_YFULL);
        tma_2d(sb + OFF_YT + 10240, &m.y, 128 * r + 64, 80 * hg, bars + 8 * B_YFULL);
      }
    }
  } else {
    asm volatile("setmaxnreg.inc.sync.aligned.u32 152;");
    if (wg < 2) {
      float acc[120];
#pragma unroll
      for (int i = 0; i < 120; i++) acc[i] = 0.f;
      const uint32_t da = desc_lo(sb + wg * 8192, 16), db = desc_lo(sb + ST_W, 8192), dc = desc_lo(sb + ST_WT, 2048);
      mbar_wait(bars + 8 * B_F0, 0);
      TSIF(w == 0 && wg == 0, 1);
      wg_fence();
#pragma unroll
      for (int k = 0; k < 4; k++) WgSST<192>::mma<HI_SW128, HI_SW128>(acc, da + 2 * k, db + 128 * k, 1);
      wg_commit();
      mbar_wait(bars + 8 * B_FULL1, 0);
      wg_fence();
#pragma unroll
      for (int k = 0; k < 4; k++) WgSST<48>::mma<HI_SW128, HI_SW32>(acc + 96, da + 2 * k, dc + 32 * k, 1);
      wg_commit();
#pragma unroll 1
      for (int kb = 1; kb < 10; kb++) {
        mbar_wait(bars + 8 * (B_FULL1 + (kb & 3)), (kb >> 2) & 1);
        const uint32_t so = (kb & 3) * (STAGE_BYTES >> 4);
        wg_fence();
#pragma unroll
        for (int k = 0; k < 4; k++) {
          WgSST<192>::mma<HI_SW128, HI_SW128>(acc, da + so + 2 * k, db + so + 128 * k, 1);
          WgSST<48>::mma<HI_SW128, HI_SW32>(acc + 96, da + so + 2 * k, dc + so + 32 * k, 1);
        }
        wg_commit();
        wg_wait<1>();
        if (lane == 0) mbar_arrive(bars + 8 * (kb == 4 ? B_E3 : B_EMPTY1 + ((kb - 1) & 3)));
      }
      mbar_wait(bars + 8 * B_EPOCH, 0);
      const uint32_t tag = lds32(sb + OFF_EPOCH) + 1;
      mbar_wait(bars + 8 * B_S3, 0);
      wg_wait<0>();
      pin<120>(acc);
      if (lane == 0) mbar_arrive(bars + 8 * B_P1);
      TSM(w == 0, 3 + wg);
      attention(acc, sb, b, wg, w, lane, tag);
    } else {
      const int tw = tid & 127, chl = 64 * (b & 1) + 8 * w + (lane >> 2);
      uint4* up = g_U + chl * U_PITCH + ((4 * (b >> 1) + (lane & 3)) ^ ((b >> 2) & 1));
      uint2 sw[10];
      uint32_t dv = 0;
      if (lane < 5) dv = __ldg(reinterpret_cast<const unsigned short*>(p.ssm_D) + 5 * b + lane);
#pragma unroll
      for (int i = 0; i < 10; i++) sw[i] = ldg64(reinterpret_cast<const uint2*>(p.shift_k) + chl + 128 * (i >> 1) + 32 * (i & 1));
      uint32_t tab[12];
      uint32_t tt[2];
      fft_tables(tab, tw);
      fft_twiddles(tt, tw);
      uint4 res[10];
#pragma unroll
      for (int i = 0; i < 10; i++) res[i] = make_uint4(0, 0, 0, 0);
#pragma unroll 1
      for (int slab = 0; slab < 5; slab++) {
#pragma unroll
        for (int i = 0; i < 8; i++) res[i] = res[i + 2];
        prep_slab(res + 8, sw, sb, slab, w, lane);
        TSIF(w == 0, 99 + 4 * slab);
#pragma unroll
        for (int i = 0; i < 8; i++) sw[i] = sw[i + 2];
      }
      TSIF(w == 0, 28);
      __syncwarp();
      if (lane == 0) mbar_arrive(bars + 8 * B_KVD + ((res[8].x ^ res[9].x) & p.zero));
      mbar_wait(bars + 8 * B_KVD, 0);
      fft_tables_store(tab, sb, tw);
      mbar_wait(bars + 8 * B_LAST, 0);
#pragma unroll
      for (int i = 0; i < 10; i++) up[(128 * (i >> 1) + 32 * (i & 1)) * U_PITCH] = res[i];
      __syncwarp();
      if (lane == 0) mbar_arrive(bars + 8 * B_PREP);
      TSIF(w == 0, 5);
      mbar_wait(bars + 8 * B_LAST, 0);
      prep_gate(p, sb, b, w, lane);
      __syncwarp();
      if (lane == 0) mbar_arrive(bars + 8 * B_GATE);
      TSIF(w == 0, 72);
      mbar_wait(bars + 8 * B_HB, 0);
      TSIF(w == 0, 2);
      const uint32_t ha = sb + U_BYTES + ((tw >> 3) * 16 + 8 + (tw & 7)) * 16;
      uint4 hv[5];
#pragma unroll
      for (int c = 0; c < 5; c++) hv[c] = lds128(ha + off_ch(c));
      __syncwarp();
#pragma unroll
      for (int c = 0; c < 5; c++) sts128((ha ^ 16) + off_ch(c), hv[c].x, hv[c].y, hv[c].z, hv[c].w);
      asm volatile("st.shared.v2.u32 [%0], {%1, %2};" ::"r"(sb + OFF_TT + 8 * tw), "r"(tt[0]), "r"(tt[1]) : "memory");
      if (tw < 5) asm volatile("st.shared.f32 [%0], %1;" ::"r"(sb + OFF_D + 4 * tw), "f"(bf_lo(dv) * 0.125f) : "memory");
      fence_async_smem();
      __syncwarp();
      if (lane == 0) mbar_arrive(bars + 8 * B_HA);
      TSIF(w == 0, 6);
    }

    FftConst fc;
    TSM(w == 0 && wg == 0, 104);
    mbar_wait(bars + 8 * B_HA, 0);
    fft_matrices(fc, sb, w, lane);
    TSM(w == 0 && wg == 0, 105);
    TSM(w == 0 && wg == 2, 124);
    if (wg == 2) filter_steps(fc, sb, w, lane);
#pragma unroll 1
    for (uint32_t tasks = wg == 0 ? TASK0 : wg == 1 ? TASK1 : TASK2; tasks; tasks >>= 4) {
      const int c = (tasks & 7) - 1;
      conv_channel(fc, sb, c, wg, w, lane);
      if (lane == 0) mbar_arrive(bars + 8 * (B_YST + c));
      TSM(w == 0, 10 + c);
    }

    if (wg != 1) {
      const int wg = warp >> 3;
      const int g = lane >> 2;
      float acc[40];
#pragma unroll
      for (int i = 0; i < 40; i++) acc[i] = 0.f;
      const uint32_t da = desc_lo(sb + wg * 1024, 2048), db = desc_lo(sb, 2560);
      mbar_wait(bars + 8 * B_ORB, 0);
      mbar_wait(bars + 8 * B_FULL2, 0);
      TSM(w == 0, 15 + wg);
#pragma unroll 1
      for (int j = 0; j < 8; j++) {
        if (j == 1 - wg) mbar_wait(bars + 8 * B_CVD, 0);
        mbar_wait(bars + 8 * (B_FULL2 + j), 0);
        TSM(w == 0 && wg == 0, 44 + (j < 4 ? j : j + 6));
        const uint32_t oa = da + (off_o(j) >> 4), ob = db + (off_w(j) >> 4);
        wg_fence();
#pragma unroll
        for (int k = 0; k < 5; k++) WgSST<80>::mma<HI_NONE, HI_SW32>(acc, oa + 256 * k, ob + 32 * k, 1);
        wg_commit();
        wg_wait<1>();
        if (j >= 1 && j <= 4 && lane == 0) mbar_arrive(bars + 8 * (B_EMPTY2 + j - 1));
      }
      TSIF(w == 0 && wg == 0, 113);
      const int tr = 64 * wg + 16 * w + (lane & 15);
      const uint32_t fm = sb + OFF_QS + tr * 128, fx = (lane >> 4) ^ (tr & 7);
      const uint32_t ft = sb + OFF_QT + tr * 32 + (((lane >> 4) ^ (tr >> 2)) & 1) * 16;
      const float g0 = __uint_as_float(lds32(sb + OFF_GATE + (64 * wg + 16 * w + g) * 4));
      const float g1 = __uint_as_float(lds32(sb + OFF_GATE + (64 * wg + 16 * w + 8 + g) * 4));
      const uint32_t ga = pack2(g0, g0), gb = pack2(g1, g1);
      const uint32_t na = pack2(1.f - g0, 1.f - g0), nb = pack2(1.f - g1, 1.f - g1);

      uint32_t qf[20];
      mbar_wait(bars + 8 * B_QF, 0);
      TSM(w == 0 && wg == 0, 99);
#pragma unroll
      for (int j = 0; j < 5; j++) ldsm4(qf + 4 * j, j < 4 ? fm + ((fx ^ (2 * j)) << 4) : ft);
#pragma unroll
      for (int i = 0; i < 20; i++) {
        qf[i] = bmul((i & 1) ? gb : ga, qf[i]);
        asm volatile("" : "+r"(qf[i]));
      }

      wg_wait<0>();
      pin<40>(acc);
      TSM(w == 0, 17 + wg);
      uint32_t pb[20];
#pragma unroll
      for (int j = 0; j < 10; j++) {
        pb[2 * j] = bmul(na, pack2(acc[4 * j], acc[4 * j + 1]));
        pb[2 * j + 1] = bmul(nb, pack2(acc[4 * j + 2], acc[4 * j + 3]));
        asm volatile("" : "+r"(pb[2 * j]), "+r"(pb[2 * j + 1]));
      }
      const uint32_t ya = sb + OFF_YT + wg * 10240 + ((lane >> 4) * 8 + (lane & 7)) * 128 +
                          (((2 * w + (((lane >> 3) & 1) ^ wg)) ^ (lane & 7)) << 4);
      mbar_wait(bars + 8 * B_YFULL, 0);
      TSM(w == 0 && wg == 0, 19);
#pragma unroll
      for (int j = 0; j < 5; j++) {
        uint32_t y[4];
        ldsm4t(y, ya + 2048 * j);
#pragma unroll
        for (int i = 0; i < 4; i++)
          qf[4 * j + i] = bfma(qf[4 * j + i], y[i], pb[4 * j + i]);
      }
#pragma unroll
      for (int j = 0; j < 5; j++) stsm4(j < 4 ? fm + ((fx ^ (2 * j)) << 4) : ft, qf + 4 * j);
      fence_async_smem();
      __syncwarp();
      if (lane == 0) {
        const int row = 64 * wg + 16 * w;
        asm volatile("cp.async.bulk.tensor.2d.global.shared::cta.bulk_group [%0, {%2, %3}], [%1];"
                     ::"l"(&m.om), "r"(sb + OFF_QS + row * 128), "r"(80 * hg), "r"(128 * r + row) : "memory");
        asm volatile("cp.async.bulk.tensor.2d.global.shared::cta.bulk_group [%0, {%2, %3}], [%1];"
                     ::"l"(&m.ot), "r"(sb + OFF_QT + row * 32), "r"(80 * hg + 64), "r"(128 * r + row) : "memory");
        asm volatile("cp.async.bulk.commit_group;\ncp.async.bulk.wait_group.read 0;" ::: "memory");
      }
      TSM(w == 0 || w == 3, 40 + 2 * wg + (w & 1));
    }
  }
}

typedef CUresult (*EncodeFn)(CUtensorMap*, CUtensorMapDataType, cuuint32_t, void*, const cuuint64_t*, const cuuint64_t*,
                             const cuuint32_t*, const cuuint32_t*, CUtensorMapInterleave, CUtensorMapSwizzle,
                             CUtensorMapL2promotion, CUtensorMapFloatOOBfill);

void encode(EncodeFn fn, CUtensorMap* tm, const void* base, int rank, const cuuint64_t* dims, const cuuint64_t* strides,
            const cuuint32_t* box, CUtensorMapSwizzle swz) {
  const cuuint32_t ones[3] = {1, 1, 1};
  fn(tm, CU_TENSOR_MAP_DATA_TYPE_BFLOAT16, rank, const_cast<void*>(base), dims, strides, box, ones,
     CU_TENSOR_MAP_INTERLEAVE_NONE, swz, CU_TENSOR_MAP_L2_PROMOTION_L2_128B, CU_TENSOR_MAP_FLOAT_OOB_FILL_NONE);
}

}

extern "C" void kernel_launch(void* const* d_in, const int* in_sizes, int n_in, void* d_out, int out_size) {
  (void)in_sizes; (void)n_in; (void)out_size;
  Params p;
  p.q = (const __nv_bfloat16*)d_in[0];
  p.k = (const __nv_bfloat16*)d_in[1];
  p.v = (const __nv_bfloat16*)d_in[2];
  p.shift_k = (const __nv_bfloat16*)d_in[3];
  p.ssm_k = (const __nv_bfloat16*)d_in[4];
  p.ssm_D = (const __nv_bfloat16*)d_in[5];
  p.wqkv = (const __nv_bfloat16*)d_in[7];
  p.wo = (const __nv_bfloat16*)d_in[8];
  p.gate_w = (const __nv_bfloat16*)d_in[9];
  p.out = (__nv_bfloat16*)d_out;
  p.zero = 0;

  static EncodeFn fn = nullptr;
  static void *yaddr = nullptr, *oaddr = nullptr;
  if (!fn) {
    cudaDriverEntryPointQueryResult qr;
    void* f = nullptr;
    cudaGetDriverEntryPoint("cuTensorMapEncodeTiled", &f, cudaEnableDefault, &qr);
    fn = (EncodeFn)f;
    cudaGetSymbolAddress(&yaddr, g_U);
    cudaGetSymbolAddress(&oaddr, g_O);
    cudaFuncSetAttribute(fused_kernel, cudaFuncAttributeMaxDynamicSharedMemorySize, SMEM_BYTES);
  }
  Maps m;
  {
    const cuuint64_t dims[3] = {640, 1024, 2}, st[2] = {2560, 1280};
    const cuuint32_t box[3] = {64, 64, 2};
    encode(fn, &m.x, p.q, 3, dims, st, box, CU_TENSOR_MAP_SWIZZLE_128B);
  }
  {
    const cuuint64_t dims[3] = {640, 640, 3}, st[2] = {3840, 1280};
    const cuuint32_t box[3] = {64, 64, 3}, boxt[3] = {16, 64, 3};
    encode(fn, &m.wm, p.wqkv, 3, dims, st, box, CU_TENSOR_MAP_SWIZZLE_128B);
    encode(fn, &m.wt, p.wqkv, 3, dims, st, boxt, CU_TENSOR_MAP_SWIZZLE_32B);
  }
  {
    const cuuint64_t dims[3] = {64, 2048, 10}, st[2] = {1280, 128};
    const cuuint32_t boxk[3] = {64, 35, 1}, boxv[3] = {64, 32, 1};
    encode(fn, &m.k, p.k, 3, dims, st, boxk, CU_TENSOR_MAP_SWIZZLE_128B);
    encode(fn, &m.v, p.v, 3, dims, st, boxv, CU_TENSOR_MAP_SWIZZLE_128B);
  }
  {
    const cuuint64_t dims[3] = {16, 640, 40}, st[2] = {1280, 32};
    const cuuint32_t box[3] = {16, 40, 5};
    encode(fn, &m.wo, p.wo, 3, dims, st, box, CU_TENSOR_MAP_SWIZZLE_32B);
  }
  {
    const cuuint64_t dims[2] = {2048, 640}, st[1] = {U_PITCH * 16};
    const cuuint32_t box[2] = {64, 80};
    encode(fn, &m.y, yaddr, 2, dims, st, box, CU_TENSOR_MAP_SWIZZLE_128B);
    const cuuint64_t dl[2] = {64, DIM * U_PITCH / 8}, dol[2] = {64, NCTA * 160}, sl[1] = {128};
    const cuuint32_t bl[2] = {16, 32}, bol[2] = {16, 160};
    encode(fn, &m.yl, yaddr, 2, dl, sl, bl, CU_TENSOR_MAP_SWIZZLE_NONE);
    encode(fn, &m.ol, oaddr, 2, dol, sl, bol, CU_TENSOR_MAP_SWIZZLE_NONE);
  }
  {
    const cuuint64_t dims[2] = {640, 2048}, st[1] = {1280};
    const cuuint32_t bqm[2] = {64, 128}, bqt[2] = {16, 128}, bom[2] = {64, 16}, bot[2] = {16, 16};
    encode(fn, &m.qm, p.q, 2, dims, st, bqm, CU_TENSOR_MAP_SWIZZLE_128B);
    encode(fn, &m.qt, p.q, 2, dims, st, bqt, CU_TENSOR_MAP_SWIZZLE_32B);
    encode(fn, &m.om, p.out, 2, dims, st, bom, CU_TENSOR_MAP_SWIZZLE_128B);
    encode(fn, &m.ot, p.out, 2, dims, st, bot, CU_TENSOR_MAP_SWIZZLE_32B);
  }
  fused_kernel<<<NCTA, NTHR, SMEM_BYTES>>>(m, p);
}
```

```cpp
#include <cuda.h>
#include <cuda_bf16.h>
#include <cuda_runtime.h>
#include <stdint.h>

namespace {

constexpr int SEQ = 2048, DIM = 640, NCTA = 128, NTHR = 512;

#define KV_KB 2
#define DEV_EXIT 0
#define FENCE_LO 0
#define FENCE_HI 0
#define WB_TRIG B_USIG
#define T_ISSUE 288
#define HPF 0
#define HPF0 0
#define T_INIT 448
#define TASK0 0x3
#define TASK1 0x52
#define TASK2 0x41

constexpr uint32_t STAGE_BYTES = 47104, ST_W = 16384, ST_WT = 40960;
constexpr uint32_t O_BYTES = 20480, WO_BYTES = 12800;
constexpr uint32_t OFF_OA = 0;
constexpr uint32_t OFF_QS = 3 * O_BYTES, OFF_QT = OFF_QS + 16384;
constexpr uint32_t OFF_WC = 81920;
constexpr uint32_t OFF_WA = 94720;
constexpr uint32_t OFF_GATE = 145920;
constexpr uint32_t OFF_TT = 146432;
constexpr uint32_t OFF_KVX = 148480;
constexpr uint32_t OFF_CH3 = 163840;
constexpr uint32_t CH_BYTES = 12288, U_BYTES = 4096;
constexpr uint32_t OFF_FT = 225280, OFF_GT = 229376;
constexpr uint32_t OFF_CH0 = 188416;
constexpr uint32_t OFF_KVS = OFF_CH0, KVS_V = 4480, KVS_BYTES = 8576;
constexpr uint32_t OFF_YT = 163840;
constexpr uint32_t OFF_BAR = 231936;
constexpr uint32_t SMEM_BYTES = OFF_BAR + 512;

enum : uint32_t {
  B_EMPTY1 = 0, B_S3 = 3, B_E3 = 4, B_EMPTY2 = 5, B_ATTN = 9, B_P1 = 10,
  B_GATE = 11, B_HA = 12, B_KVD = 13, B_PREP = 14, B_YST = 15,
  B_CVD = 20,
  B_FULL2 = 21, B_U = 29, B_KV = 33, B_HB = 38, B_C34 = 39, B_YRB = 40, B_YFULL = 41, B_EPOCH = 42, B_LAST = 43,
  B_WOP = 44, B_USIG = 45, B_WST = 46, B_QF = 47, B_ORB = 48,
  B_F0 = 49, B_FULL1 = 50
};
constexpr uint32_t OFF_EPOCH = OFF_BAR + 8 * 58, OFF_D = OFF_BAR + 8 * 60;
__device__ __forceinline__ uint32_t off_o(int j) { return j < 4 ? OFF_OA + j * O_BYTES : j < 6 ? OFF_CH0 + (j - 4) * O_BYTES : OFF_OA + (j - 6) * O_BYTES; }
__device__ __forceinline__ uint32_t off_w(int j) { return j < 4 ? OFF_WA + j * WO_BYTES : j == 4 ? OFF_KVX : j == 5 ? OFF_WC : OFF_WA + (j - 6) * WO_BYTES; }
__device__ __forceinline__ int step_src(int hg, int j) { return j == 0 ? hg : j <= hg ? j - 1 : j; }
__device__ __forceinline__ bool tail_first(int hg) { return (hg & 3) == 3; }
__device__ __forceinline__ uint32_t off_ch(int c) { return (c < 3 ? OFF_CH0 : OFF_CH3 - 3 * CH_BYTES) + c * CH_BYTES; }

#define U_PITCH 264
__device__ __align__(1024) uint4 g_U[DIM * U_PITCH];
__device__ __align__(128) uint4 g_O[NCTA * 1280];
__device__ uint4 g_WO[64 * 800];
__device__ uint4 g_halo[NCTA * 2 * 7 * 32];
__device__ __align__(128) float g_gate[SEQ];
__device__ unsigned g_cnt[32 * (1 + 2 * 16 + 8 + NCTA)];
constexpr int C_LAUNCH = 0, C_PREP = 32, C_Y = 32 * 17, C_W = 32 * 33, C_O = 32 * 41;

#define TSM(cond, slot) do { } while (0)
#define TSIF(cond, slot) do { if (__LINE__ >= FENCE_LO && __LINE__ < FENCE_HI) sched_fence(); } while (0)
__device__ __forceinline__ void sched_fence() {
  asm volatile("{\n.reg .pred p;\n.reg .u32 c;\nmov.u32 c, %%clock;\nsetp.eq.u32 p, c, 0;\n@p st.shared.u32 [%0], c;\n}"
               ::"r"(1024 + OFF_EPOCH + 4) : "memory");
}
#define TS(slot) TSIF(true, slot)

struct Params {
  const __nv_bfloat16 *q, *k, *v, *shift_k, *ssm_k, *ssm_D, *wqkv, *wo, *gate_w;
  __nv_bfloat16* out;
  uint32_t zero;
};

constexpr int SPIN_LIMIT = 1 << 17;

__device__ __forceinline__ void mbar_init(uint32_t bar, uint32_t count) {
  asm volatile("mbarrier.init.shared::cta.b64 [%0], %1;" ::"r"(bar), "r"(count) : "memory");
}
__device__ __forceinline__ void mbar_expect_tx(uint32_t bar, uint32_t bytes) {
  asm volatile("mbarrier.arrive.expect_tx.shared::cta.b64 _, [%0], %1;" ::"r"(bar), "r"(bytes) : "memory");
}
__device__ __forceinline__ void mbar_arrive(uint32_t bar) {
  asm volatile("mbarrier.arrive.shared::cta.b64 _, [%0];" ::"r"(bar) : "memory");
}
__device__ __forceinline__ void mbar_wait(uint32_t bar, uint32_t parity) {
  uint32_t ok;
  int spins = 0;
  do {
      asm volatile("{\n.reg .pred p;\nmbarrier.try_wait.parity.shared::cta.b64 p, [%1], %2;\nselp.b32 %0, 1, 0, p;\n}"
                   : "=r"(ok) : "r"(bar), "r"(parity) : "memory");
    if (++spins > SPIN_LIMIT) break;
  } while (!ok);
}
__device__ __forceinline__ unsigned flag_read(const unsigned* p) {
  unsigned v;
  asm volatile("ld.relaxed.gpu.global.u32 %0, [%1];" : "=r"(v) : "l"(p) : "memory");
  return v;
}
__device__ __forceinline__ void flag_poll(const unsigned* p, unsigned target) {
  unsigned v;
  int spins = 0;
  do {
    asm volatile("ld.relaxed.gpu.global.u32 %0, [%1];" : "=r"(v) : "l"(p) : "memory");
    if (++spins > SPIN_LIMIT) break;
  } while ((int)(v - target) < 0);
}
__device__ __forceinline__ void flag_wait(const unsigned* p, unsigned target) {
  flag_poll(p, target);
}
__device__ __forceinline__ void flag_signal(unsigned* p, int n, int lane) {
  if (lane == 0) asm volatile("fence.release.gpu;" ::: "memory");
  __syncwarp();
  if (lane < n) asm volatile("red.relaxed.gpu.global.add.u32 [%0], 1;" ::"l"(p + 32 * lane) : "memory");
}
__device__ __forceinline__ void flag_bump(unsigned* p) {
  asm volatile("red.relaxed.gpu.global.add.u32 [%0], 1;" ::"l"(p) : "memory");
}
__device__ __forceinline__ void fence_async_smem() { asm volatile("fence.proxy.async.shared::cta;" ::: "memory"); }
__device__ __forceinline__ void wg_sync(int id) { asm volatile("bar.sync %0, 128;" ::"r"(id) : "memory"); }

__device__ __forceinline__ void tma_2d(uint32_t dst, const CUtensorMap* tm, int c0, int c1, uint32_t bar) {
  asm volatile("cp.async.bulk.tensor.2d.shared::cluster.global.mbarrier::complete_tx::bytes [%0], [%1, {%3, %4}], [%2];"
               ::"r"(dst), "l"(tm), "r"(bar), "r"(c0), "r"(c1) : "memory");
}
__device__ __forceinline__ void tma_3d(uint32_t dst, const CUtensorMap* tm, int c0, int c1, int c2, uint32_t bar) {
  asm volatile("cp.async.bulk.tensor.3d.shared::cluster.global.mbarrier::complete_tx::bytes [%0], [%1, {%3, %4, %5}], [%2];"
               ::"r"(dst), "l"(tm), "r"(bar), "r"(c0), "r"(c1), "r"(c2) : "memory");
}
__device__ __forceinline__ void bulk_load(uint32_t dst, const void* src, uint32_t bytes, uint32_t bar) {
  asm volatile("cp.async.bulk.shared::cluster.global.mbarrier::complete_tx::bytes [%0], [%1], %2, [%3];"
               ::"r"(dst), "l"(src), "r"(bytes), "r"(bar) : "memory");
}
__device__ __forceinline__ void bulk_store(void* dst, uint32_t src, uint32_t bytes) {
  asm volatile("cp.async.bulk.global.shared::cta.bulk_group [%0], [%1], %2;" ::"l"(dst), "r"(src), "r"(bytes) : "memory");
}
__device__ __forceinline__ void bulk_wait_read() {
  asm volatile("cp.async.bulk.commit_group;\ncp.async.bulk.wait_group.read 0;" ::: "memory");
}

__device__ __forceinline__ void publish(void* dst, uint32_t src, uint32_t bytes) {
  bulk_store(dst, src, bytes);
  bulk_wait_read();
}

__device__ __forceinline__ void wg_fence() { asm volatile("wgmma.fence.sync.aligned;" ::: "memory"); }
__device__ __forceinline__ void wg_commit() { asm volatile("wgmma.commit_group.sync.aligned;" ::: "memory"); }
template <int N> __device__ __forceinline__ void wg_wait() { asm volatile("wgmma.wait_group.sync.aligned %0;" ::"n"(N) : "memory"); }
__device__ __forceinline__ uint32_t desc_lo(uint32_t addr, uint32_t lbo) { return ((addr & 0x3FFFF) >> 4) | ((lbo >> 4) << 16); }
constexpr uint32_t desc_hi(uint32_t sbo, uint32_t swz) { return (sbo >> 4) | (swz << 30); }
constexpr uint32_t HI_SW128 = desc_hi(1024, 1), HI_SW64 = desc_hi(512, 2), HI_SW32 = desc_hi(256, 3), HI_NONE = desc_hi(128, 0);
template <int N> __device__ __forceinline__ void pin(float* d) {
#pragma unroll
  for (int i = 0; i < N; i++) asm volatile("" : "+f"(d[i])::"memory");
}

__device__ __forceinline__ uint32_t lds32(uint32_t a) {
  uint32_t v;
  asm volatile("ld.volatile.shared.u32 %0, [%1];" : "=r"(v) : "r"(a) : "memory");
  return v;
}
__device__ __forceinline__ uint2 ldg64(const void* a) {
  uint2 v;
  asm volatile("ld.global.nc.v2.u32 {%0, %1}, [%2];" : "=r"(v.x), "=r"(v.y) : "l"(a) : "memory");
  return v;
}
__device__ __forceinline__ void ldsm4(uint32_t* r, uint32_t a) {
  asm volatile("ldmatrix.sync.aligned.m8n8.x4.shared.b16 {%0, %1, %2, %3}, [%4];"
               : "=r"(r[0]), "=r"(r[1]), "=r"(r[2]), "=r"(r[3]) : "r"(a) : "memory");
}
__device__ __forceinline__ void ldsm4t(uint32_t* r, uint32_t a) {
  asm volatile("ldmatrix.sync.aligned.m8n8.x4.trans.shared.b16 {%0, %1, %2, %3}, [%4];"
               : "=r"(r[0]), "=r"(r[1]), "=r"(r[2]), "=r"(r[3]) : "r"(a) : "memory");
}
__device__ __forceinline__ uint2 lds64(uint32_t a) {
  uint2 v;
  asm volatile("ld.shared.v2.u32 {%0, %1}, [%2];" : "=r"(v.x), "=r"(v.y) : "r"(a) : "memory");
  return v;
}
__device__ __forceinline__ uint4 lds128(uint32_t a) {
  uint4 v;
  asm volatile("ld.shared.v4.u32 {%0, %1, %2, %3}, [%4];" : "=r"(v.x), "=r"(v.y), "=r"(v.z), "=r"(v.w) : "r"(a) : "memory");
  return v;
}
__device__ __forceinline__ void sts128(uint32_t a, uint32_t x, uint32_t y, uint32_t z, uint32_t w) {
  asm volatile("st.shared.v4.u32 [%0], {%1, %2, %3, %4};" ::"r"(a), "r"(x), "r"(y), "r"(z), "r"(w) : "memory");
}
__device__ __forceinline__ void stsm4(uint32_t a, const uint32_t* r) {
  asm volatile("stmatrix.sync.aligned.m8n8.x4.shared.b16 [%0], {%1, %2, %3, %4};" ::"r"(a), "r"(r[0]), "r"(r[1]), "r"(r[2]), "r"(r[3]) : "memory");
}
__device__ __forceinline__ uint32_t pack2(float lo, float hi) {
  uint32_t r;
  asm("cvt.rn.bf16x2.f32 %0, %1, %2;" : "=r"(r) : "f"(hi), "f"(lo));
  return r;
}
__device__ __forceinline__ uint32_t movm(uint32_t a) {
  uint32_t d;
  asm volatile("movmatrix.sync.aligned.m8n8.trans.b16 %0, %1;" : "=r"(d) : "r"(a));
  return d;
}
__device__ __forceinline__ uint32_t bmul(uint32_t a, uint32_t b) {
  uint32_t d;
  asm("mul.rn.bf16x2 %0, %1, %2;" : "=r"(d) : "r"(a), "r"(b));
  return d;
}
__device__ __forceinline__ uint32_t badd(uint32_t a, uint32_t b) {
  uint32_t d;
  asm("add.rn.bf16x2 %0, %1, %2;" : "=r"(d) : "r"(a), "r"(b));
  return d;
}
__device__ __forceinline__ uint32_t bfma(uint32_t a, uint32_t b, uint32_t c) {
  uint32_t d;
  asm("fma.rn.bf16x2 %0, %1, %2, %3;" : "=r"(d) : "r"(a), "r"(b), "r"(c));
  return d;
}
__device__ __forceinline__ float bf_lo(uint32_t x) { return __uint_as_float(x << 16); }
__device__ __forceinline__ float bf_hi(uint32_t x) { return __uint_as_float(x & 0xFFFF0000u); }
__device__ __forceinline__ float ex2(float x) {
  float y;
  asm("ex2.approx.ftz.f32 %0, %1;" : "=f"(y) : "f"(x));
  return y;
}
__device__ __forceinline__ float rcp(float x) {
  float y;
  asm("rcp.approx.ftz.f32 %0, %1;" : "=f"(y) : "f"(x));
  return y;
}
__device__ __forceinline__ void mma16816(float* d, uint32_t a0, uint32_t a1, uint32_t a2, uint32_t a3, uint32_t b0, uint32_t b1) {
  asm volatile("mma.sync.aligned.m16n8k16.row.col.f32.bf16.bf16.f32 {%0, %1, %2, %3}, {%4, %5, %6, %7}, {%8, %9}, {%0, %1, %2, %3};"
               : "+f"(d[0]), "+f"(d[1]), "+f"(d[2]), "+f"(d[3])
               : "r"(a0), "r"(a1), "r"(a2), "r"(a3), "r"(b0), "r"(b1));
}
__device__ __forceinline__ void mma1688(float* d, uint32_t a0, uint32_t a1, uint32_t b0) {
  asm volatile("mma.sync.aligned.m16n8k8.row.col.f32.bf16.bf16.f32 {%0, %1, %2, %3}, {%4, %5}, {%6}, {%0, %1, %2, %3};"
               : "+f"(d[0]), "+f"(d[1]), "+f"(d[2]), "+f"(d[3])
               : "r"(a0), "r"(a1), "r"(b0));
}

template <int N> struct WgRS;
template <int N> struct WgSST;
template <> struct WgRS<32> {
  template <uint32_t HB>
  static __device__ __forceinline__ void mma(float* d, const uint32_t* a, uint32_t db) {
    asm volatile("{\n.reg .pred p;\n.reg .b64 db;\nsetp.ne.b32 p, %22, 0;\n"
      "mov.b64 db, {%20, %21};\n"
      "wgmma.mma_async.sync.aligned.m64n32k16.f32.bf16.bf16 {"
      "%0, %1, %2, %3, %4, %5, %6, %7, %8, %9, %10, %11, %12, %13, %14, %15"
      "}, {%16, %17, %18, %19}, db, p, 1, 1, 1;\n}\n"
      : "+f"(d[0]), "+f"(d[1]), "+f"(d[2]), "+f"(d[3]), "+f"(d[4]), "+f"(d[5]), "+f"(d[6]), "+f"(d[7]),
        "+f"(d[8]), "+f"(d[9]), "+f"(d[10]), "+f"(d[11]), "+f"(d[12]), "+f"(d[13]), "+f"(d[14]), "+f"(d[15])
      : "r"(a[0]), "r"(a[1]), "r"(a[2]), "r"(a[3]), "r"(db), "n"(HB), "n"(1));
  }
  template <uint32_t HB>
  static __device__ __forceinline__ void set(float* d, const uint32_t* a, uint32_t db) {
    asm volatile("{\n.reg .pred p;\n.reg .b64 db;\nsetp.ne.b32 p, %22, 0;\n"
      "mov.b64 db, {%20, %21};\n"
      "wgmma.mma_async.sync.aligned.m64n32k16.f32.bf16.bf16 {"
      "%0, %1, %2, %3, %4, %5, %6, %7, %8, %9, %10, %11, %12, %13, %14, %15"
      "}, {%16, %17, %18, %19}, db, p, 1, 1, 1;\n}\n"
      : "=f"(d[0]), "=f"(d[1]), "=f"(d[2]), "=f"(d[3]), "=f"(d[4]), "=f"(d[5]), "=f"(d[6]), "=f"(d[7]),
        "=f"(d[8]), "=f"(d[9]), "=f"(d[10]), "=f"(d[11]), "=f"(d[12]), "=f"(d[13]), "=f"(d[14]), "=f"(d[15])
      : "r"(a[0]), "r"(a[1]), "r"(a[2]), "r"(a[3]), "r"(db), "n"(HB), "n"(0));
  }
};
template <> struct WgRS<64> {
  template <uint32_t HB>
  static __device__ __forceinline__ void mma(float* d, const uint32_t* a, uint32_t db) {
    asm volatile("{\n.reg .pred p;\n.reg .b64 db;\nsetp.ne.b32 p, %38, 0;\n"
      "mov.b64 db, {%36, %37};\n"
      "wgmma.mma_async.sync.aligned.m64n64k16.f32.bf16.bf16 {"
      "%0, %1, %2, %3, %4, %5, %6, %7, %8, %9, %10, %11, %12, %13, %14, %15, "
      "%16, %17, %18, %19, %20, %21, %22, %23, %24, %25, %26, %27, %28, %29, %30, %31"
      "}, {%32, %33, %34, %35}, db, p, 1, 1, 1;\n}\n"
      : "+f"(d[0]), "+f"(d[1]), "+f"(d[2]), "+f"(d[3]), "+f"(d[4]), "+f"(d[5]), "+f"(d[6]), "+f"(d[7]),
        "+f"(d[8]), "+f"(d[9]), "+f"(d[10]), "+f"(d[11]), "+f"(d[12]), "+f"(d[13]), "+f"(d[14]), "+f"(d[15]),
        "+f"(d[16]), "+f"(d[17]), "+f"(d[18]), "+f"(d[19]), "+f"(d[20]), "+f"(d[21]), "+f"(d[22]), "+f"(d[23]),
        "+f"(d[24]), "+f"(d[25]), "+f"(d[26]), "+f"(d[27]), "+f"(d[28]), "+f"(d[29]), "+f"(d[30]), "+f"(d[31])
      : "r"(a[0]), "r"(a[1]), "r"(a[2]), "r"(a[3]), "r"(db), "n"(HB), "n"(1));
  }
  template <uint32_t HB>
  static __device__ __forceinline__ void set(float* d, const uint32_t* a, uint32_t db) {
    asm volatile("{\n.reg .pred p;\n.reg .b64 db;\nsetp.ne.b32 p, %38, 0;\n"
      "mov.b64 db, {%36, %37};\n"
      "wgmma.mma_async.sync.aligned.m64n64k16.f32.bf16.bf16 {"
      "%0, %1, %2, %3, %4, %5, %6, %7, %8, %9, %10, %11, %12, %13, %14, %15, "
      "%16, %17, %18, %19, %20, %21, %22, %23, %24, %25, %26, %27, %28, %29, %30, %31"
      "}, {%32, %33, %34, %35}, db, p, 1, 1, 1;\n}\n"
      : "=f"(d[0]), "=f"(d[1]), "=f"(d[2]), "=f"(d[3]), "=f"(d[4]), "=f"(d[5]), "=f"(d[6]), "=f"(d[7]),
        "=f"(d[8]), "=f"(d[9]), "=f"(d[10]), "=f"(d[11]), "=f"(d[12]), "=f"(d[13]), "=f"(d[14]), "=f"(d[15]),
        "=f"(d[16]), "=f"(d[17]), "=f"(d[18]), "=f"(d[19]), "=f"(d[20]), "=f"(d[21]), "=f"(d[22]), "=f"(d[23]),
        "=f"(d[24]), "=f"(d[25]), "=f"(d[26]), "=f"(d[27]), "=f"(d[28]), "=f"(d[29]), "=f"(d[30]), "=f"(d[31])
      : "r"(a[0]), "r"(a[1]), "r"(a[2]), "r"(a[3]), "r"(db), "n"(HB), "n"(0));
  }
};
template <> struct WgSST<48> {
  template <uint32_t HA, uint32_t HB>
  static __device__ __forceinline__ void mma(float* d, uint32_t da, uint32_t db, int sc) {
    asm volatile("{\n.reg .pred p;\n.reg .b64 da, db;\nsetp.ne.b32 p, %28, 0;\n"
      "mov.b64 da, {%24, %25};\nmov.b64 db, {%26, %27};\n"
      "wgmma.mma_async.sync.aligned.m64n48k16.f32.bf16.bf16 {"
      "%0, %1, %2, %3, %4, %5, %6, %7, %8, %9, %10, %11, %12, %13, %14, %15, "
      "%16, %17, %18, %19, %20, %21, %22, %23"
      "}, da, db, p, 1, 1, 0, 1;\n}\n"
      : "+f"(d[0]), "+f"(d[1]), "+f"(d[2]), "+f"(d[3]), "+f"(d[4]), "+f"(d[5]), "+f"(d[6]), "+f"(d[7]),
        "+f"(d[8]), "+f"(d[9]), "+f"(d[10]), "+f"(d[11]), "+f"(d[12]), "+f"(d[13]), "+f"(d[14]), "+f"(d[15]),
        "+f"(d[16]), "+f"(d[17]), "+f"(d[18]), "+f"(d[19]), "+f"(d[20]), "+f"(d[21]), "+f"(d[22]), "+f"(d[23])
      : "r"(da), "n"(HA), "r"(db), "n"(HB), "r"(sc));
  }
};
template <> struct WgSST<80> {
  template <uint32_t HA, uint32_t HB>
  static __device__ __forceinline__ void mma(float* d, uint32_t da, uint32_t db, int sc) {
    asm volatile("{\n.reg .pred p;\n.reg .b64 da, db;\nsetp.ne.b32 p, %44, 0;\n"
      "mov.b64 da, {%40, %41};\nmov.b64 db, {%42, %43};\n"
      "wgmma.mma_async.sync.aligned.m64n80k16.f32.bf16.bf16 {"
      "%0, %1, %2, %3, %4, %5, %6, %7, %8, %9, %10, %11, %12, %13, %14, %15, "
      "%16, %17, %18, %19, %20, %21, %22, %23, %24, %25, %26, %27, %28, %29, %30, %31, "
      "%32, %33, %34, %35, %36, %37, %38, %39"
      "}, da, db, p, 1, 1, 0, 1;\n}\n"
      : "+f"(d[0]), "+f"(d[1]), "+f"(d[2]), "+f"(d[3]), "+f"(d[4]), "+f"(d[5]), "+f"(d[6]), "+f"(d[7]),
        "+f"(d[8]), "+f"(d[9]), "+f"(d[10]), "+f"(d[11]), "+f"(d[12]), "+f"(d[13]), "+f"(d[14]), "+f"(d[15]),
        "+f"(d[16]), "+f"(d[17]), "+f"(d[18]), "+f"(d[19]), "+f"(d[20]), "+f"(d[21]), "+f"(d[22]), "+f"(d[23]),
        "+f"(d[24]), "+f"(d[25]), "+f"(d[26]), "+f"(d[27]), "+f"(d[28]), "+f"(d[29]), "+f"(d[30]), "+f"(d[31]),
        "+f"(d[32]), "+f"(d[33]), "+f"(d[34]), "+f"(d[35]), "+f"(d[36]), "+f"(d[37]), "+f"(d[38]), "+f"(d[39])
      : "r"(da), "n"(HA), "r"(db), "n"(HB), "r"(sc));
  }
};
template <> struct WgSST<192> {
  template <uint32_t HA, uint32_t HB>
  static __device__ __forceinline__ void mma(float* d, uint32_t da, uint32_t db, int sc) {
    asm volatile("{\n.reg .pred p;\n.reg .b64 da, db;\nsetp.ne.b32 p, %100, 0;\n"
      "mov.b64 da, {%96, %97};\nmov.b64 db, {%98, %99};\n"
      "wgmma.mma_async.sync.aligned.m64n192k16.f32.bf16.bf16 {"
      "%0, %1, %2, %3, %4, %5, %6, %7, %8, %9, %10, %11, %12, %13, %14, %15, "
      "%16, %17, %18, %19, %20, %21, %22, %23, %24, %25, %26, %27, %28, %29, %30, %31, "
      "%32, %33, %34, %35, %36, %37, %38, %39, %40, %41, %42, %43, %44, %45, %46, %47, "
      "%48, %49, %50, %51, %52, %53, %54, %55, %56, %57, %58, %59, %60, %61, %62, %63, "
      "%64, %65, %66, %67, %68, %69, %70, %71, %72, %73, %74, %75, %76, %77, %78, %79, "
      "%80, %81, %82, %83, %84, %85, %86, %87, %88, %89, %90, %91, %92, %93, %94, %95"
      "}, da, db, p, 1, 1, 0, 1;\n}\n"
      : "+f"(d[0]), "+f"(d[1]), "+f"(d[2]), "+f"(d[3]), "+f"(d[4]), "+f"(d[5]), "+f"(d[6]), "+f"(d[7]),
        "+f"(d[8]), "+f"(d[9]), "+f"(d[10]), "+f"(d[11]), "+f"(d[12]), "+f"(d[13]), "+f"(d[14]), "+f"(d[15]),
        "+f"(d[16]), "+f"(d[17]), "+f"(d[18]), "+f"(d[19]), "+f"(d[20]), "+f"(d[21]), "+f"(d[22]), "+f"(d[23]),
        "+f"(d[24]), "+f"(d[25]), "+f"(d[26]), "+f"(d[27]), "+f"(d[28]), "+f"(d[29]), "+f"(d[30]), "+f"(d[31]),
        "+f"(d[32]), "+f"(d[33]), "+f"(d[34]), "+f"(d[35]), "+f"(d[36]), "+f"(d[37]), "+f"(d[38]), "+f"(d[39]),
        "+f"(d[40]), "+f"(d[41]), "+f"(d[42]), "+f"(d[43]), "+f"(d[44]), "+f"(d[45]), "+f"(d[46]), "+f"(d[47]),
        "+f"(d[48]), "+f"(d[49]), "+f"(d[50]), "+f"(d[51]), "+f"(d[52]), "+f"(d[53]), "+f"(d[54]), "+f"(d[55]),
        "+f"(d[56]), "+f"(d[57]), "+f"(d[58]), "+f"(d[59]), "+f"(d[60]), "+f"(d[61]), "+f"(d[62]), "+f"(d[63]),
        "+f"(d[64]), "+f"(d[65]), "+f"(d[66]), "+f"(d[67]), "+f"(d[68]), "+f"(d[69]), "+f"(d[70]), "+f"(d[71]),
        "+f"(d[72]), "+f"(d[73]), "+f"(d[74]), "+f"(d[75]), "+f"(d[76]), "+f"(d[77]), "+f"(d[78]), "+f"(d[79]),
        "+f"(d[80]), "+f"(d[81]), "+f"(d[82]), "+f"(d[83]), "+f"(d[84]), "+f"(d[85]), "+f"(d[86]), "+f"(d[87]),
        "+f"(d[88]), "+f"(d[89]), "+f"(d[90]), "+f"(d[91]), "+f"(d[92]), "+f"(d[93]), "+f"(d[94]), "+f"(d[95])
      : "r"(da), "n"(HA), "r"(db), "n"(HB), "r"(sc));
  }
};

struct FftConst {
  uint32_t f[2][4], fi[4][4];
  uint32_t ta[2][2], tb[2][2];
};
__device__ __forceinline__ void cis(int m, float scale, float& c, float& s) {
  const float a = (float)m * (-6.283185307179586f * scale);
  c = __cosf(a);
  s = __sinf(a);
}
__device__ __forceinline__ void fft_tables(uint32_t (&v)[12], int tw) {
  const int row = tw >> 2, ch = tw & 3;
#pragma unroll
  for (int i = 0; i < 4; i++) {
    float c[2], s[2], x[2];
#pragma unroll
    for (int e = 0; e < 2; e++) {
      cis((((32 * (8 * ch + 2 * i + e) + 15) * (4 * row - 63) + 2048) & 4095) - 2048, 1.f / 4096, c[e], s[e]);
      float gc, gs;
      cis((((row & 15) * (8 * (ch & 1) + 2 * i + e) + 8) & 15) - 8, 1.f / 16, gc, gs);
      x[e] = (row >> 4) == (ch >> 1) ? gc : (ch >> 1) ? gs : -gs;
    }
    v[i] = pack2(c[0] * 0.125f, c[1] * 0.125f);
    v[4 + i] = pack2(s[0] * 0.125f, s[1] * 0.125f);
    v[8 + i] = pack2(x[0], x[1]);
  }
#pragma unroll
  for (int i = 0; i < 12; i++) asm volatile("" : "+r"(v[i]));
}
__device__ __forceinline__ void fft_tables_store(const uint32_t (&v)[12], uint32_t sb, int tw) {
  const int row = tw >> 2;
  const uint32_t x = ((tw ^ (row >> 1)) & 3) << 4, a = sb + OFF_FT + (16 * (row >> 3) + (row & 7)) * 64 + x;
  sts128(a, v[0], v[1], v[2], v[3]);
  sts128(a + 512, v[4], v[5], v[6], v[7]);
  sts128(sb + OFF_GT + row * 64 + x, v[8], v[9], v[10], v[11]);
}
__device__ __forceinline__ void fft_twiddles(uint32_t (&v)[2], int tw) {
  float a[2], s[2];
#pragma unroll
  for (int i = 0; i < 2; i++) {
    float c;
    cis((2 * (2 * (tw & 3) + i) - 15) * (4 * (tw >> 2) - 63), 1.f / 4096, c, s[i]);
    a[i] = __fdividef(-s[i], 1.f + c);
  }
  v[0] = pack2(a[0], a[1]);
  v[1] = pack2(s[0], s[1]);
  asm volatile("" : "+r"(v[0]), "+r"(v[1]));
}
__device__ __forceinline__ void fft_matrices(FftConst& k, uint32_t sb, int w, int lane) {
  const uint32_t x = (lane >> 1) & 3;
  const uint2 t0 = lds64(sb + OFF_TT + 256 * w + 8 * lane), t1 = lds64(sb + OFF_TT + 256 * w + 8 * (lane ^ 3));
  k.ta[0][0] = t0.x;
  k.tb[0][0] = t0.y;
  k.ta[1][1] = __byte_perm(t1.x, 0, 0x1032);
  k.tb[1][1] = __byte_perm(t1.y, 0, 0x1032);
#pragma unroll
  for (int j = 0; j < 2; j++) {
    k.ta[1 - j][j] = k.ta[j][j] ^ 0x80008000u;
    k.tb[1 - j][j] = k.tb[j][j] ^ 0x80008000u;
    asm volatile("" : "+r"(k.ta[0][j]), "+r"(k.tb[0][j]), "+r"(k.ta[1][j]), "+r"(k.tb[1][j]));
  }
#pragma unroll
  for (int i = 0; i < 2; i++) {
    ldsm4(k.f[i], sb + OFF_FT + (16 * w + (lane & 15)) * 64 + (((2 * i + (lane >> 4)) ^ x) << 4));
    ldsm4t(k.fi[i], sb + OFF_FT + (32 * i + lane) * 64 + ((w ^ x) << 4));
#pragma unroll
    for (int j = 0; j < 4; j++) {
      k.fi[2 + i][j] = (j & 1) ? k.fi[i][j - 1] ^ 0x80008000u : k.fi[i][j + 1];
      asm volatile("" : "+r"(k.fi[2 + i][j]));
    }
  }
}
__device__ __forceinline__ void rot(uint32_t& x, uint32_t& y, uint32_t a, uint32_t b) {
  x = bfma(a, y, x);
  y = bfma(b, x, y);
  x = bfma(a, y, x);
}
__device__ __forceinline__ void twiddle_fwd(uint32_t (&a)[4][4], float* d, const FftConst& k) {
#pragma unroll
  for (int q = 0; q < 4; q++)
#pragma unroll
    for (int j = 0; j < 2; j++) {
      const float* x = d + 8 * q + 4 * j;
      uint32_t re = pack2(x[0], x[1]), im = pack2(x[2], x[3]);
      rot(re, im, k.ta[0][j], k.tb[0][j]);
      a[q & 2][2 * j + (q & 1)] = re;
      a[(q & 2) + 1][2 * j + (q & 1)] = im;
    }
}
__device__ __forceinline__ void g_step(float* d, const uint32_t (&a)[4][4], uint32_t dre, uint32_t dim) {
  WgRS<32>::set<HI_SW64>(d, a[0], dre);
  WgRS<32>::set<HI_SW64>(d + 16, a[2], dre);
  WgRS<32>::mma<HI_SW64>(d, a[1], dim);
  WgRS<32>::mma<HI_SW64>(d + 16, a[3], dim);
  wg_commit();
}

__device__ __forceinline__ void products(uint32_t (&a)[4][4], const float* H, const float* U, int p) {
#pragma unroll
  for (int j = 0; j < 2; j++)
#pragma unroll
    for (int m = 2 * p; m < 2 * p + 2; m++) {
      float pr[2], pi[2];
#pragma unroll
      for (int x = 0; x < 2; x++)
#pragma unroll
        for (int q = 0; q <= m; q++) {
          const int ih = 16 * (q >> 1) + 2 * (q & 1) + 4 * j + x, iu = 16 * ((m - q) >> 1) + 2 * ((m - q) & 1) + 4 * j + x;
          pr[x] = q ? fmaf(H[ih], U[iu], pr[x]) : H[ih] * U[iu];
          pi[x] = q ? fmaf(H[ih], U[iu + 8], pi[x]) : H[ih] * U[iu + 8];
          pr[x] = fmaf(-H[ih + 8], U[iu + 8], pr[x]);
          pi[x] = fmaf(H[ih + 8], U[iu], pi[x]);
        }
      a[m & 2][2 * j + (m & 1)] = pack2(pr[0], pr[1]);
      a[(m & 2) + 1][2 * j + (m & 1)] = pack2(pi[0], pi[1]);
    }
}

__device__ __forceinline__ void conv_channel(const FftConst& k, uint32_t sb, int c, int wg, int w, int lane) {
  const uint32_t cb = sb + off_ch(c), bars = sb + OFF_BAR;
  const uint32_t du = desc_lo(cb, 1024), dg = desc_lo(sb + OFF_GT, 16), dz = desc_lo(cb + U_BYTES, 16);
  float U[32], H[32];
  uint32_t a[4][4], e[4][4];
  const float dv = __uint_as_float(lds32(sb + OFF_D + 4 * c));
  wg_fence();
  WgRS<64>::set<HI_SW32>(H, k.f[0], du + 256);
  WgRS<64>::mma<HI_SW32>(H, k.f[1], du + 256 + 32);
  wg_commit();
  wg_wait<0>();
  pin<32>(H);
  twiddle_fwd(a, H, k);
  mbar_wait(bars + 8 * (B_U + (c < 3 ? c : 3)), 0);
  TSM(w == 0 && c < 3, 7 + wg);
  wg_fence();
  WgRS<64>::set<HI_SW32>(U, k.f[0], du);
  WgRS<64>::mma<HI_SW32>(U, k.f[1], du + 32);
  wg_commit();
  g_step(H, a, dg, dg + 64);
  wg_wait<1>();
  pin<32>(U);
  twiddle_fwd(e, U, k);
  wg_fence();
  g_step(U, e, dg, dg + 64);
  wg_wait<0>();
  pin<32>(U);
  pin<32>(H);
#pragma unroll
  for (int j = 0; j < 4; j++) H[4 * (j >> 1) + (j & 1)] += dv;
  float V[32];
#pragma unroll
  for (int p = 0; p < 2; p++) {
    products(a, H, U, p);
    wg_fence();
    WgRS<32>::set<HI_SW64>(V + 16 * p, a[2 * p], dg + 64);
    WgRS<32>::mma<HI_SW64>(V + 16 * p, a[2 * p + 1], dg);
    wg_commit();
  }
  const uint32_t za = cb + U_BYTES + (8 * w + (lane & 7)) * 128 + (((lane >> 3) ^ (lane & 7)) << 4);
  const uint32_t ya = cb + (lane >> 4) * 1024 + (8 * w + (lane & 7)) * 32 + ((((lane >> 3) ^ (lane >> 2)) & 1) << 4);
  wg_sync(1 + wg);
#pragma unroll
  for (int p = 0; p < 2; p++) {
    if (p == 0) wg_wait<1>();
    else wg_wait<0>();
    pin<16>(V + 16 * p);
#pragma unroll
    for (int i = 0; i < 4; i++) {
      const int j = i & 1;
      const float* x = V + 16 * p + 4 * j + (i & 2);
      e[p][i] = pack2(x[8], x[9]);
      e[2 + p][i] = pack2(x[0], x[1]);
      rot(e[p][i], e[2 + p][i], k.ta[1][j], k.tb[1][j]);
    }
    stsm4(za ^ (64 * p), e[p]);
    stsm4((za ^ (64 * p)) + 4096, e[2 + p]);
  }
  fence_async_smem();
  wg_sync(1 + wg);
  wg_fence();
  WgRS<64>::set<HI_SW128>(H, k.fi[0], dz);
#pragma unroll
  for (int ks = 1; ks < 4; ks++) WgRS<64>::mma<HI_SW128>(H, k.fi[ks], dz + 128 * ks);
  wg_commit();
  wg_wait<0>();
  pin<32>(H);
  if (lane == 0) mbar_arrive(bars + 8 * B_CVD);
  TSIF(w == 0, 88 + c);
#pragma unroll
  for (int j = 0; j < 8; j++)
    a[j >> 2][j & 3] = j < 2 ? pack2(H[4 * j], H[4 * j + 1]) : pack2(H[4 * j] + H[4 * j - 6], H[4 * j + 1] + H[4 * j - 5]);
  stsm4(ya, a[0]);
  stsm4(ya + 2048, a[1]);
  fence_async_smem();
  __syncwarp();
}

__device__ __forceinline__ void prep_slab(uint4* res, const uint2* sw, uint32_t sb, int slab, int w, int lane) {
  const int t = lane & 3, tp = (lane & 7) >> 1, pos = 8 * tp + 2 * (((lane >> 3) + tp) & 3) + (lane & 1);
  const uint32_t base = sb + OFF_KVS + slab * KVS_BYTES + pos * 128;
  uint32_t kk[2][4][4], vv[2][4];
  mbar_wait(sb + OFF_BAR + 8 * (B_KV + slab), 0);
#pragma unroll
  for (int h = 0; h < 2; h++) {
#pragma unroll
    for (int j = 0; j < 4; j++) {
      const uint32_t a = base + 128 * j;
      ldsm4t(kk[h][j], a + (((w + 4 * h) ^ ((a >> 7) & 7)) << 4));
    }
    const uint32_t a = base + KVS_V;
    ldsm4t(vv[h], a + (((w + 4 * h) ^ ((a >> 7) & 7)) << 4));
  }
#pragma unroll
  for (int h = 0; h < 2; h++) {
    uint32_t (&k)[4][4] = kk[h];
    uint32_t (&v)[4] = vv[h];
    const uint32_t w0 = __byte_perm(sw[h].x, 0, 0x1010), w1 = __byte_perm(sw[h].x, 0, 0x3232);
    const uint32_t w2 = __byte_perm(sw[h].y, 0, 0x1010), w3 = __byte_perm(sw[h].y, 0, 0x3232);
#pragma unroll
    for (int m = 0; m < 4; m++)
      v[m] = bmul(badd(badd(badd(bmul(k[0][m], w3), bmul(k[1][m], w2)), bmul(k[2][m], w1)), bmul(k[3][m], w0)), v[m]);
    uint32_t a[4];
#pragma unroll
    for (int m = 0; m < 4; m++) a[m] = (t & 1) ? v[(m + 3) & 3] : v[m];
    res[h] = (t & 2) ? make_uint4(a[2], a[3], a[0], a[1]) : make_uint4(a[0], a[1], a[2], a[3]);
  }
}

__device__ __forceinline__ void prep_gate(const Params& p, uint32_t sb, int b, int w, int lane) {
  uint2 gw[5], x[4][5];
#pragma unroll
  for (int j = 0; j < 5; j++) gw[j] = ldg64(reinterpret_cast<const uint2*>(p.gate_w) + lane + 32 * j);
#pragma unroll
  for (int i = 0; i < 4; i++)
#pragma unroll
    for (int j = 0; j < 5; j++)
      x[i][j] = ldg64(reinterpret_cast<const uint2*>(p.q) + (16 * b + 4 * w + i) * (DIM / 4) + lane + 32 * j);
  float s[4];
#pragma unroll
  for (int i = 0; i < 4; i++) {
    s[i] = 0.f;
#pragma unroll
    for (int j = 0; j < 5; j++) {
      const uint32_t m0 = bmul(x[i][j].x, gw[j].x), m1 = bmul(x[i][j].y, gw[j].y);
      s[i] += (bf_lo(m0) + bf_hi(m0)) + (bf_lo(m1) + bf_hi(m1));
    }
  }
  const bool h = lane & 16, q = lane & 8;
  const float a = (h ? s[2] : s[0]) + __shfl_xor_sync(0xffffffffu, h ? s[0] : s[2], 16);
  const float c = (h ? s[3] : s[1]) + __shfl_xor_sync(0xffffffffu, h ? s[1] : s[3], 16);
  float z = (q ? c : a) + __shfl_xor_sync(0xffffffffu, q ? a : c, 8);
#pragma unroll
  for (int o = 4; o > 0; o >>= 1) z += __shfl_xor_sync(0xffffffffu, z, o);
  z = bf_lo(pack2(z, 0.f));
  z = bf_lo(pack2(__fdividef(1.f, 1.f + __expf(-z)), 0.f));
  mbar_wait(sb + OFF_BAR + 8 * B_S3, 0);
  if ((lane & 7) == 0) asm volatile("st.shared.f32 [%0], %1;" ::"r"(sb + OFF_GATE + 64 * (b & 7) + 16 * w + (lane >> 1)), "f"(z) : "memory");
  fence_async_smem();
}

__device__ __forceinline__ uint32_t bmax(uint32_t a, uint32_t b) {
  uint32_t d;
  asm("max.bf16x2 %0, %1, %2;" : "=r"(d) : "r"(a), "r"(b));
  return d;
}
__device__ __forceinline__ void softmax_two(const float (&l)[2][2], uint32_t& p0, uint32_t& p1) {
  constexpr float kScale = 0.22360679774997896f, kLog2e = 1.4426950408889634f;
  const uint32_t r0 = pack2(l[0][0], l[1][0]), r1 = pack2(l[0][1], l[1][1]);
  const uint32_t x0 = pack2(bf_lo(r0) * kScale, bf_hi(r0) * kScale), x1 = pack2(bf_lo(r1) * kScale, bf_hi(r1) * kScale);
  uint32_t m = bmax(x0, x1);
  m = bmax(m, __shfl_xor_sync(0xffffffffu, m, 1));
  m = bmax(m, __shfl_xor_sync(0xffffffffu, m, 2));
  const float m0 = bf_lo(m) * kLog2e, m1 = bf_hi(m) * kLog2e;
  p0 = pack2(ex2(bf_lo(x0) * kLog2e - m0), ex2(bf_lo(x1) * kLog2e - m0));
  p1 = pack2(ex2(bf_hi(x0) * kLog2e - m1), ex2(bf_hi(x1) * kLog2e - m1));
}

__device__ __forceinline__ void halo_read(uint32_t (&kpv)[10], uint32_t (&vpv)[10], uint32_t (&tg)[7], const uint4* hp) {
#pragma unroll
  for (int j = 0; j < 7; j++) {
    uint32_t x0, x1, x2;
    asm volatile("ld.relaxed.gpu.global.v4.u32 {%0, %1, %2, %3}, [%4];"
                 : "=r"(x0), "=r"(x1), "=r"(x2), "=r"(tg[j]) : "l"(hp + 32 * j) : "memory");
    if (j < 4) kpv[3 * j] = x0; else vpv[3 * j - 10] = x0;
    if (j < 3) kpv[3 * j + 1] = x1; else vpv[3 * j - 9] = x1;
    if (j < 3) kpv[3 * j + 2] = x2; else if (j < 6) vpv[3 * j - 8] = x2;
  }
}

template <int ROT>
__device__ __forceinline__ void pack_qkv(const float* acc, uint32_t (&qlo)[10], uint32_t (&qhi)[10], uint32_t (&klo)[10],
                                         uint32_t (&khi)[10], uint32_t (&vlo)[10], uint32_t (&vhi)[10]) {
#pragma unroll
  for (int j = 0; j < 10; j++) {
    const int x = (j + ROT) % 10, tq = x < 8 ? x : 16 + x, tk = x < 8 ? 8 + x : 18 + x, tv = x < 8 ? 16 + x : 20 + x;
    khi[j] = pack2(acc[4 * tk + 2], acc[4 * tk + 3]);
    vhi[j] = movm(pack2(acc[4 * tv + 2], acc[4 * tv + 3]));
    qlo[j] = pack2(acc[4 * tq], acc[4 * tq + 1]);
    qhi[j] = pack2(acc[4 * tq + 2], acc[4 * tq + 3]);
    klo[j] = pack2(acc[4 * tk], acc[4 * tk + 1]);
    vlo[j] = pack2(acc[4 * tv], acc[4 * tv + 1]);
    asm volatile("" : "+r"(khi[j]), "+r"(qlo[j]), "+r"(qhi[j]), "+r"(klo[j]), "+r"(vlo[j]));
  }
}

template <int ROT> __device__ __forceinline__ void halo_send(const float* acc, uint4* ho, uint32_t tag) {
#pragma unroll
  for (int j = 0; j < 7; j++) {
    uint32_t x[3];
#pragma unroll
    for (int e = 0; e < 3; e++) {
      const int i = 3 * j + e, y = (i % 10 + ROT) % 10, tk = y < 8 ? 8 + y : 18 + y, tv = y < 8 ? 16 + y : 20 + y;
      x[e] = i < 10 ? pack2(acc[4 * tk + 2], acc[4 * tk + 3]) : i < 20 ? movm(pack2(acc[4 * tv + 2], acc[4 * tv + 3])) : 0u;
    }
    asm volatile("st.relaxed.gpu.global.v4.u32 [%0], {%1, %2, %3, %4};" ::"l"(ho + 32 * j), "r"(x[0]), "r"(x[1]), "r"(x[2]), "r"(tag) : "memory");
  }
}

__device__ __forceinline__ void attention(float* acc, uint32_t sb, int b, int par, int w, int lane, uint32_t tag) {
  const int g = lane >> 2, t = lane & 3;
  uint32_t klo[10], khi[10], vlo[10], vhi[10], qlo[10], qhi[10], kpv[10], vpv[10];
  if (w == 3 && b < NCTA - 8) {
    uint4* ho = g_halo + (b * 2 + par) * 224 + lane;
    if (tail_first(b & 7)) halo_send<8>(acc, ho, tag);
    else halo_send<0>(acc, ho, tag);
    TSIF(par == 0, 76);
    pin<120>(acc);
  }
  if (tail_first(b & 7)) pack_qkv<8>(acc, qlo, qhi, klo, khi, vlo, vhi);
  else pack_qkv<0>(acc, qlo, qhi, klo, khi, vlo, vhi);
  const uint32_t xa = sb + OFF_KVX + (par * 3) * 2560 + lane * 16;
  if (w < 3) {
    sts128(xa + w * 2560, khi[0], khi[1], khi[2], khi[3]);
    sts128(xa + w * 2560 + 512, khi[4], khi[5], khi[6], khi[7]);
    sts128(xa + w * 2560 + 1024, khi[8], khi[9], vhi[0], vhi[1]);
    sts128(xa + w * 2560 + 1536, vhi[2], vhi[3], vhi[4], vhi[5]);
    sts128(xa + w * 2560 + 2048, vhi[6], vhi[7], vhi[8], vhi[9]);
  }
  TSIF(par == 0 && w == 1, 64);
#pragma unroll
  for (int j = 0; j < 10; j++) vlo[j] = movm(vlo[j]);
  const bool far0 = 2 * t > g, far1 = 2 * t + 1 > g;
  const uint32_t mfar = (far0 ? 0x0000FFFFu : 0u) | (far1 ? 0xFFFF0000u : 0u);
  float slo[4][2], lg[2][2];
  uint32_t phi[4], plo[4], qml[4], qmh[4];
#pragma unroll
  for (int h = 0; h < 4; h++) {
    const int f = h == 0 ? 0 : h == 1 ? 3 : h == 2 ? 5 : 8, hf = h < 2 ? 2 : 7;
    const bool mine = (h & 1) ? t >= 2 : t < 2;
    qml[h] = mine ? qlo[hf] : 0u;
    qmh[h] = mine ? qhi[hf] : 0u;
    float a[4] = {0.f, 0.f, 0.f, 0.f}, c[4] = {0.f, 0.f, 0.f, 0.f};
    mma16816(a, qlo[f], qhi[f], qlo[f + 1], qhi[f + 1], klo[f], klo[f + 1]);
    mma16816(c, qlo[f], qhi[f], qlo[f + 1], qhi[f + 1], khi[f], khi[f + 1]);
    mma1688(a, qml[h], qmh[h], klo[hf]);
    mma1688(c, qml[h], qmh[h], khi[hf]);
    slo[h][0] = a[0];
    slo[h][1] = a[1];
    lg[h & 1][0] = far0 ? a[2] : c[2];
    lg[h & 1][1] = far1 ? a[3] : c[3];
    if (h & 1) softmax_two(lg, phi[h - 1], phi[h]);
  }
  TSIF(par == 0 && w == 1, 65);
  wg_sync(1 + par);
  TSIF(par == 0 && w == 1, 66);
  const bool nohist = (w == 0) && (b < 8);
  const uint4* hp = g_halo + ((b - 8) * 2 + par) * 224 + lane;
  uint32_t tg[7];
  if (w > 0) {
    const uint4 v0 = lds128(xa + (w - 1) * 2560), v1 = lds128(xa + (w - 1) * 2560 + 512), v2 = lds128(xa + (w - 1) * 2560 + 1024);
    const uint4 v3 = lds128(xa + (w - 1) * 2560 + 1536), v4 = lds128(xa + (w - 1) * 2560 + 2048);
    kpv[0] = v0.x; kpv[1] = v0.y; kpv[2] = v0.z; kpv[3] = v0.w; kpv[4] = v1.x; kpv[5] = v1.y; kpv[6] = v1.z; kpv[7] = v1.w;
    kpv[8] = v2.x; kpv[9] = v2.y; vpv[0] = v2.z; vpv[1] = v2.w; vpv[2] = v3.x; vpv[3] = v3.y; vpv[4] = v3.z; vpv[5] = v3.w;
    vpv[6] = v4.x; vpv[7] = v4.y; vpv[8] = v4.z; vpv[9] = v4.w;
  } else if (nohist) {
#pragma unroll
    for (int j = 0; j < 10; j++) kpv[j] = vpv[j] = 0u;
  } else {
    TSIF(par == 0, 77);
    halo_read(kpv, vpv, tg, hp);
  }
  if (w == 0 && !nohist) {
    int spins = 0;
    while (true) {
      bool ok = true;
#pragma unroll
      for (int j = 0; j < 7; j++) ok = ok && tg[j] == tag;
      if (__all_sync(0xffffffffu, ok) || ++spins > SPIN_LIMIT) break;
      halo_read(kpv, vpv, tg, hp);
    }
    TSIF(par == 0, 79);
  }
#pragma unroll
  for (int h = 0; h < 4; h++) {
    const int f = h == 0 ? 0 : h == 1 ? 3 : h == 2 ? 5 : 8, hf = h < 2 ? 2 : 7;
    float a[4] = {0.f, 0.f, 0.f, 0.f};
    mma16816(a, qlo[f], qhi[f], qlo[f + 1], qhi[f + 1], kpv[f], kpv[f + 1]);
    mma1688(a, qml[h], qmh[h], kpv[hf]);
    const float ninf = __int_as_float(0xff800000);
    lg[h & 1][0] = far0 ? (nohist ? ninf : a[0]) : slo[h][0];
    lg[h & 1][1] = far1 ? (nohist ? ninf : a[1]) : slo[h][1];
    if (h & 1) softmax_two(lg, plo[h - 1], plo[h]);
  }
  TSIF(par == 0 && w <= 1, 67 + w);
  uint32_t ov[20];
#pragma unroll
  for (int hp = 0; hp < 2; hp++) {
    const int hf = hp ? 7 : 2;
    float sh[4] = {0.f, 0.f, 0.f, 0.f}, i0 = 0.f, i1 = 0.f;
#pragma unroll
    for (int e = 0; e < 2; e++) {
      const int h = 2 * hp + e, f = h == 0 ? 0 : h == 1 ? 3 : h == 2 ? 5 : 8;
      const uint32_t a0 = plo[h] & mfar, a2 = plo[h] & ~mfar, a3 = phi[h] & mfar, c1 = phi[h] & ~mfar;
      float sum[4] = {0.f, 0.f, 0.f, 0.f};
      mma1688(sum, plo[h], phi[h], 0x3F803F80u);
      const float r0 = rcp(sum[0]), r1 = rcp(sum[2]);
#pragma unroll
      for (int j = f; j < f + 2; j++) {
        float o[4] = {0.f, 0.f, 0.f, 0.f};
        mma16816(o, a0, 0u, a2, a3, vpv[j], vlo[j]);
        mma1688(o, 0u, c1, vhi[j]);
        ov[2 * j] = pack2(o[0] * r0, o[1] * r0);
        ov[2 * j + 1] = pack2(o[2] * r1, o[3] * r1);
      }
      const bool mine = e ? g >= 4 : g < 4;
      mma16816(sh, a0, 0u, a2, a3, mine ? vpv[hf] : 0u, mine ? vlo[hf] : 0u);
      mma1688(sh, 0u, c1, mine ? vhi[hf] : 0u);
      if (e == 0 || t >= 2) {
        i0 = r0;
        i1 = r1;
      }
    }
    ov[2 * hf] = pack2(sh[0] * i0, sh[1] * i0);
    ov[2 * hf + 1] = pack2(sh[2] * i1, sh[3] * i1);
  }
  TS(32 + 4 * par + w);
  mbar_wait(sb + OFF_BAR + 8 * B_P1, 0);
  const uint32_t oa = sb + OFF_OA + (lane >> 4) * 2048 + (32 * w + 2 * (lane & 15) + par) * 16;
#pragma unroll
  for (int j = 0; j < 5; j++) stsm4(oa + 4096 * j, ov + 4 * j);
  TSIF(par == 0 && w == 0, 120);
  fence_async_smem();
  TSIF(par == 0 && w == 0, 121);
  __syncwarp();
  if (lane == 0) mbar_arrive(sb + OFF_BAR + 8 * B_ATTN);
  TSM(w == 0 || w == 2, 122 + par + (w == 2 ? 3 : 0));
}

struct Maps {
  CUtensorMap x, wm, wt, k, v, y, wo, qm, qt, om, ot, yl, ol;
};

__device__ __forceinline__ void load_stage(uint32_t sb, int kb, int b, const Maps& m) {
  const uint32_t st = sb + (kb & 3) * STAGE_BYTES, bar = sb + OFF_BAR + 8 * (B_FULL1 + (kb & 3));
  const int r = b >> 3, hg = b & 7, slab = kb - KV_KB;
  const bool kv = slab >= 0 && slab < 5;
  const uint32_t kbar = sb + OFF_BAR + 8 * (B_KV + slab), dst = sb + OFF_KVS + slab * KVS_BYTES;
  mbar_expect_tx(bar, STAGE_BYTES);
  if (kv) mbar_expect_tx(kbar, KVS_BYTES);
  tma_3d(st, &m.x, 64 * kb, 64 * r, 0, bar);
  tma_3d(st + ST_W, &m.wm, 80 * hg + (tail_first(hg) ? 16 : 0), 64 * kb, 0, bar);
  tma_3d(st + ST_WT, &m.wt, 80 * hg + (tail_first(hg) ? 0 : 64), 64 * kb, 0, bar);
  if (kv) tma_3d(dst, &m.k, 0, 32 * (b >> 1) - 3, 2 * slab + (b & 1), kbar);
  if (kv) tma_3d(dst + KVS_V, &m.v, 0, 32 * (b >> 1), 2 * slab + (b & 1), kbar);
}

__global__ void __launch_bounds__(NTHR, 1) fused_kernel(const __grid_constant__ Maps m, const Params p) {
  extern __shared__ __align__(1024) uint8_t smem[];
  const uint32_t sb = (uint32_t)__cvta_generic_to_shared(smem);
  const uint32_t bars = sb + OFF_BAR;
  const int tid = threadIdx.x, lane = tid & 31;
  int b = blockIdx.x;
  b = (((b & 63) >> 3) * 2 + (b & 1)) * 8 + (((b < 64 ? 0x6521 : 0x7430) >> (4 * ((b >> 1) & 3))) & 7);
  const int r = b >> 3, hg = b & 7;

  if (tid == T_ISSUE) {
    TSM(true, 0);
    mbar_init(bars + 8 * B_F0, 1);
    fence_async_smem();
    mbar_expect_tx(bars + 8 * B_F0, ST_WT);
    tma_3d(sb, &m.x, 0, 64 * r, 0, bars + 8 * B_F0);
    tma_3d(sb + ST_W, &m.wm, 80 * hg + (tail_first(hg) ? 16 : 0), 0, 0, bars + 8 * B_F0);
#pragma unroll
    for (int i = 0; i < 4; i++) mbar_init(bars + 8 * (B_FULL1 + i), 1);
    fence_async_smem();
    mbar_expect_tx(bars + 8 * B_FULL1, STAGE_BYTES - ST_WT);
    tma_3d(sb + ST_WT, &m.wt, 80 * hg + (tail_first(hg) ? 0 : 64), 0, 0, bars + 8 * B_FULL1);
    load_stage(sb, 1, b, m);
  } else if (tid == T_INIT) {
#pragma unroll
    for (int i = 0; i < B_F0; i++) mbar_init(bars + 8 * i, i < B_GATE ? 8 : i < B_CVD ? 4 : i == B_CVD ? 20 : 1);
    fence_async_smem();
  }
  const int warp = __shfl_sync(0xffffffffu, tid >> 5, 0), wg = warp >> 2, w = warp & 3;
  __syncthreads();

  if (wg == 3) {
    asm volatile("setmaxnreg.dec.sync.aligned.u32 56;");
    if (w == 0) {
      if (lane == 0) {
#pragma unroll 1
        for (int kb = 2; kb < 10; kb++) {
          if (kb >= 4) mbar_wait(bars + 8 * (kb == 7 ? B_E3 : B_EMPTY1 + (kb & 3)), (kb >> 3) & 1);
          TSIF(kb >= 4, 44 + kb);
          load_stage(sb, kb, b, m);
          TSIF(kb == 3, 60);
          if (kb == 9) mbar_arrive(bars + 8 * B_LAST);
        }
        mbar_wait(bars + 8 * B_WOP, 0);
        mbar_wait(bars + 8 * B_EPOCH, 0);
        flag_wait(g_cnt + C_W + 32 * hg, (lds32(sb + OFF_EPOCH) + 1) * 16);
        TS(30);
#pragma unroll 1
        for (int j = 0; j < 8; j++) {
          if (j >= 6) mbar_wait(bars + 8 * (B_EMPTY2 + j - 6), 0);
          if (j == 4) mbar_wait(bars + 8 * B_ORB, 0);
          TSIF(j >= 6, 100 + j);
          mbar_expect_tx(bars + 8 * (B_FULL2 + j), j == 0 ? WO_BYTES : j == 5 ? O_BYTES + WO_BYTES + 512 : O_BYTES + WO_BYTES);
          bulk_load(sb + off_w(j), g_WO + (hg * 8 + step_src(hg, j)) * 800, WO_BYTES, bars + 8 * (B_FULL2 + j));
        }
        mbar_wait(bars + 8 * (B_EMPTY2 + 3), 0);
        mbar_expect_tx(bars + 8 * B_QF, O_BYTES);
        tma_2d(sb + OFF_QS, &m.qm, 80 * hg, 128 * r, bars + 8 * B_QF);
        tma_2d(sb + OFF_QT, &m.qt, 80 * hg + 64, 128 * r, bars + 8 * B_QF);
      }
    } else if (w == 1) {
      unsigned epoch = 0;
      if (lane == 0) {
        epoch = atomicAdd(g_cnt + C_LAUNCH, 1u) / NCTA;
        asm volatile("st.shared.u32 [%0], %1;" ::"r"(sb + OFF_EPOCH), "r"(epoch) : "memory");
        mbar_arrive(bars + 8 * B_EPOCH);
        if (HPF) {
          mbar_wait(bars + 8 * (HPF), 0);
          asm volatile("cp.async.bulk.prefetch.L2.global [%0], %1;" ::"l"(p.ssm_k + (5 * b + HPF0) * SEQ), "n"((5 - HPF0) * 4096) : "memory");
        }
        mbar_wait(bars + 8 * B_KVD, 0);
        mbar_expect_tx(bars + 8 * B_HB, 5 * 4096);
#pragma unroll 1
        for (int c = 0; c < 5; c++) {
          if (c == 3) mbar_wait(bars + 8 * B_S3, 0);
          bulk_load(sb + off_ch(c) + U_BYTES, p.ssm_k + (5 * b + c) * SEQ, 4096, bars + 8 * B_HB);
        }
#pragma unroll
        for (int c = 0; c < 4; c++) mbar_expect_tx(bars + 8 * (B_U + c), c < 3 ? U_BYTES : 2 * U_BYTES);
        const uint4* usrc = g_U + 5 * b * U_PITCH;
        mbar_wait(bars + 8 * B_USIG, 0);
        flag_wait(g_cnt + C_PREP + 32 * (b & 15), (epoch + 1) * NCTA);
        TS(23);
#pragma unroll
        for (int c = 0; c < 5; c++) {
          if (c == 3) mbar_wait(bars + 8 * (B_U + 2), 0);
          bulk_load(sb + off_ch(c), usrc + c * U_PITCH, U_BYTES, bars + 8 * (B_U + (c < 3 ? c : 3)));
          TSIF(c == 0 || c == 4, 116 + (c >> 2));
        }
      }
      epoch = __shfl_sync(0xffffffffu, epoch, 0);
      if (lane < 8) {
        const int src = (b & ~7) | step_src(hg, lane);
        mbar_wait(bars + 8 * B_ATTN, 0);
        TS(20);
        bool seen = false;
#pragma unroll 1
        for (int spins = 0; spins < SPIN_LIMIT; spins++) {
          const bool now = !seen && (int)(flag_read(g_cnt + C_O + 32 * src) - (epoch + 1)) >= 0;
          if (now && lane >= 1 && lane < 4) bulk_load(sb + off_o(lane), g_O + src * 1280, O_BYTES, bars + 8 * (B_FULL2 + lane));
          seen = seen || now;
          if (__all_sync(0xff, seen)) break;
        }
        TS(21);
        if (lane == 5) bulk_load(sb + OFF_GATE, g_gate + 128 * r, 512, bars + 8 * (B_FULL2 + 5));
#pragma unroll 1
        for (int j = 4; j < 8; j++) {
          if (lane == j) {
            mbar_wait(bars + 8 * (j < 6 ? B_C34 : B_EMPTY2 + j - 6), 0);
            bulk_load(sb + off_o(j), g_O + src * 1280, O_BYTES, bars + 8 * (B_FULL2 + j));
          }
          __syncwarp(0xff);
        }
        TS(22);
      }
    } else if (w == 2) {
      mbar_wait(bars + 8 * B_PREP, 0);
      flag_signal(g_cnt + C_PREP, 16, lane);
      TS(25);
      if (lane == 0) {
        mbar_arrive(bars + 8 * B_USIG);
        mbar_expect_tx(bars + 8 * B_ORB, O_BYTES / 4 + 64);
        mbar_wait(bars + 8 * B_GATE, 0);
        publish(g_gate + 16 * b, sb + OFF_GATE + 64 * hg, 64);
        bulk_load(sb + OFF_GATE + 64 * hg, g_gate + 16 * b, 64, bars + 8 * B_ORB);
        mbar_wait(bars + 8 * B_ATTN, 0);
        publish(g_O + b * 1280, sb + OFF_OA, O_BYTES);
        tma_2d(sb + OFF_KVX + 10240, &m.ol, 48, b * 160, bars + 8 * B_ORB);
        TS(74);
        mbar_wait(bars + 8 * B_ORB, 0);
        flag_bump(g_cnt + C_O + 32 * b);
        TS(26);
      }
    } else {
      if (lane == 0) {
        uint4* dst = g_WO + (hg * 8 + (r >> 1)) * 800 + (r & 1) * 80;
        mbar_wait(bars + 8 * B_S3, 0);
        asm volatile("cp.async.bulk.prefetch.L2.global [%0], 6400;" ::"l"(p.wo + b * 3200) : "memory");
        mbar_wait(bars + 8 * B_P1, 0);
        mbar_wait(bars + 8 * WB_TRIG, 0);
        mbar_expect_tx(bars + 8 * B_WST, WO_BYTES / 2);
        tma_3d(sb + OFF_WA, &m.wo, 0, 40 * r, 5 * hg, bars + 8 * B_WST);
        mbar_wait(bars + 8 * B_WST, 0);
#pragma unroll 1
        for (int n = 0; n < 5; n++) bulk_store(dst + 160 * n, sb + OFF_WA + 1280 * n, 1280);
        bulk_wait_read();
        mbar_expect_tx(bars + 8 * B_WST, WO_BYTES / 2);
#pragma unroll 1
        for (int n = 0; n < 5; n++) bulk_load(sb + OFF_WA + 1280 * n, dst + 160 * n, 1280, bars + 8 * B_WST);
        mbar_wait(bars + 8 * B_WST, 1);
        flag_bump(g_cnt + C_W + 32 * hg);
        mbar_arrive(bars + 8 * B_WOP);
        TS(71);
        mbar_expect_tx(bars + 8 * B_C34, 3 * (U_BYTES / 4));
        mbar_expect_tx(bars + 8 * B_YRB, 2 * (U_BYTES / 4));
#pragma unroll 1
        for (int c = 0; c < 5; c++) {
          mbar_wait(bars + 8 * (B_YST + c), 0);
          publish(g_U + (5 * b + c) * U_PITCH, sb + off_ch(c), U_BYTES);
          tma_2d(sb + off_ch(c), &m.yl, 48, (5 * b + c) * (U_PITCH / 8), bars + 8 * (c < 3 ? B_C34 : B_YRB));
        }
        TS(75);
        mbar_wait(bars + 8 * B_C34, 0);
        mbar_wait(bars + 8 * B_YRB, 0);
        flag_bump(g_cnt + C_Y + 32 * (b >> 4));
        TS(27);
        mbar_expect_tx(bars + 8 * B_YFULL, 20480);
        flag_wait(g_cnt + C_Y + 32 * hg, (lds32(sb + OFF_EPOCH) + 1) * 16);
        TS(24);
        tma_2d(sb + OFF_YT, &m.y, 128 * r, 80 * hg, bars + 8 * B_YFULL);
        tma_2d(sb + OFF_YT + 10240, &m.y, 128 * r + 64, 80 * hg, bars + 8 * B_YFULL);
      }
    }
  } else {
    asm volatile("setmaxnreg.inc.sync.aligned.u32 152;");
    if (wg < 2) {
      float acc[120];
#pragma unroll
      for (int i = 0; i < 120; i++) acc[i] = 0.f;
      const uint32_t da = desc_lo(sb + wg * 8192, 16), db = desc_lo(sb + ST_W, 8192), dc = desc_lo(sb + ST_WT, 2048);
      mbar_wait(bars + 8 * B_F0, 0);
      TSIF(w == 0 && wg == 0, 1);
      wg_fence();
#pragma unroll
      for (int k = 0; k < 4; k++) WgSST<192>::mma<HI_SW128, HI_SW128>(acc, da + 2 * k, db + 128 * k, 1);
      wg_commit();
      mbar_wait(bars + 8 * B_FULL1, 0);
      wg_fence();
#pragma unroll
      for (int k = 0; k < 4; k++) WgSST<48>::mma<HI_SW128, HI_SW32>(acc + 96, da + 2 * k, dc + 32 * k, 1);
      wg_commit();
#pragma unroll 1
      for (int kb = 1; kb < 10; kb++) {
        mbar_wait(bars + 8 * (B_FULL1 + (kb & 3)), (kb >> 2) & 1);
        const uint32_t so = (kb & 3) * (STAGE_BYTES >> 4);
        wg_fence();
#pragma unroll
        for (int k = 0; k < 4; k++) {
          WgSST<192>::mma<HI_SW128, HI_SW128>(acc, da + so + 2 * k, db + so + 128 * k, 1);
          WgSST<48>::mma<HI_SW128, HI_SW32>(acc + 96, da + so + 2 * k, dc + so + 32 * k, 1);
        }
        wg_commit();
        wg_wait<1>();
        if (lane == 0) mbar_arrive(bars + 8 * (kb == 4 ? B_E3 : B_EMPTY1 + ((kb - 1) & 3)));
      }
      mbar_wait(bars + 8 * B_EPOCH, 0);
      const uint32_t tag = lds32(sb + OFF_EPOCH) + 1;
      mbar_wait(bars + 8 * B_S3, 0);
      wg_wait<0>();
      pin<120>(acc);
      if (lane == 0) mbar_arrive(bars + 8 * B_P1);
      TSM(w == 0, 3 + wg);
      attention(acc, sb, b, wg, w, lane, tag);
    } else {
      const int tw = tid & 127, chl = 64 * (b & 1) + 8 * w + (lane >> 2);
      uint4* up = g_U + chl * U_PITCH + ((4 * (b >> 1) + (lane & 3)) ^ ((b >> 2) & 1));
      uint2 sw[10];
      uint32_t dv = 0;
      if (lane < 5) dv = __ldg(reinterpret_cast<const unsigned short*>(p.ssm_D) + 5 * b + lane);
#pragma unroll
      for (int i = 0; i < 10; i++) sw[i] = ldg64(reinterpret_cast<const uint2*>(p.shift_k) + chl + 128 * (i >> 1) + 32 * (i & 1));
      uint32_t tab[12];
      uint32_t tt[2];
      fft_tables(tab, tw);
      fft_twiddles(tt, tw);
      uint4 res[10];
#pragma unroll
      for (int i = 0; i < 10; i++) res[i] = make_uint4(0, 0, 0, 0);
#pragma unroll 1
      for (int slab = 0; slab < 5; slab++) {
#pragma unroll
        for (int i = 0; i < 8; i++) res[i] = res[i + 2];
        prep_slab(res + 8, sw, sb, slab, w, lane);
        TSIF(w == 0, 99 + 4 * slab);
#pragma unroll
        for (int i = 0; i < 8; i++) sw[i] = sw[i + 2];
      }
      TSIF(w == 0, 28);
      __syncwarp();
      if (lane == 0) mbar_arrive(bars + 8 * B_KVD + ((res[8].x ^ res[9].x) & p.zero));
      mbar_wait(bars + 8 * B_KVD, 0);
      fft_tables_store(tab, sb, tw);
      mbar_wait(bars + 8 * B_LAST, 0);
#pragma unroll
      for (int i = 0; i < 10; i++) up[(128 * (i >> 1) + 32 * (i & 1)) * U_PITCH] = res[i];
      __syncwarp();
      if (lane == 0) mbar_arrive(bars + 8 * B_PREP);
      TSIF(w == 0, 5);
      mbar_wait(bars + 8 * B_LAST, 0);
      prep_gate(p, sb, b, w, lane);
      __syncwarp();
      if (lane == 0) mbar_arrive(bars + 8 * B_GATE);
      TSIF(w == 0, 72);
      mbar_wait(bars + 8 * B_HB, 0);
      TSIF(w == 0, 2);
      const uint32_t ha = sb + U_BYTES + ((tw >> 3) * 16 + 8 + (tw & 7)) * 16;
      uint4 hv[5];
#pragma unroll
      for (int c = 0; c < 5; c++) hv[c] = lds128(ha + off_ch(c));
      __syncwarp();
#pragma unroll
      for (int c = 0; c < 5; c++) sts128((ha ^ 16) + off_ch(c), hv[c].x, hv[c].y, hv[c].z, hv[c].w);
      asm volatile("st.shared.v2.u32 [%0], {%1, %2};" ::"r"(sb + OFF_TT + 8 * tw), "r"(tt[0]), "r"(tt[1]) : "memory");
      if (tw < 5) asm volatile("st.shared.f32 [%0], %1;" ::"r"(sb + OFF_D + 4 * tw), "f"(bf_lo(dv) * 0.125f) : "memory");
      fence_async_smem();
      __syncwarp();
      if (lane == 0) mbar_arrive(bars + 8 * B_HA);
      TSIF(w == 0, 6);
    }

    FftConst fc;
    TSM(w == 0 && wg == 0, 104);
    mbar_wait(bars + 8 * B_HA, 0);
    fft_matrices(fc, sb, w, lane);
    TSM(w == 0 && wg == 0, 105);
    TSM(w == 0 && wg == 2, 124);
#pragma unroll 1
    for (uint32_t tasks = wg == 0 ? TASK0 : wg == 1 ? TASK1 : TASK2; tasks; tasks >>= 4) {
      const int c = (tasks & 7) - 1;
      conv_channel(fc, sb, c, wg, w, lane);
      if (lane == 0) mbar_arrive(bars + 8 * (B_YST + c));
      TSM(w == 0, 10 + c);
    }

    if (wg != 1) {
      const int wg = warp >> 3;
      const int g = lane >> 2;
      float acc[40];
#pragma unroll
      for (int i = 0; i < 40; i++) acc[i] = 0.f;
      const uint32_t da = desc_lo(sb + wg * 1024, 2048), db = desc_lo(sb, 2560);
      mbar_wait(bars + 8 * B_ORB, 0);
      mbar_wait(bars + 8 * B_FULL2, 0);
      TSM(w == 0, 15 + wg);
#pragma unroll 1
      for (int j = 0; j < 8; j++) {
        if (j == 1 - wg) mbar_wait(bars + 8 * B_CVD, 0);
        mbar_wait(bars + 8 * (B_FULL2 + j), 0);
        TSM(w == 0 && wg == 0, 44 + (j < 4 ? j : j + 6));
        const uint32_t oa = da + (off_o(j) >> 4), ob = db + (off_w(j) >> 4);
        wg_fence();
#pragma unroll
        for (int k = 0; k < 5; k++) WgSST<80>::mma<HI_NONE, HI_SW32>(acc, oa + 256 * k, ob + 32 * k, 1);
        wg_commit();
        wg_wait<1>();
        if (j >= 1 && j <= 4 && lane == 0) mbar_arrive(bars + 8 * (B_EMPTY2 + j - 1));
      }
      TSIF(w == 0 && wg == 0, 113);
      const int tr = 64 * wg + 16 * w + (lane & 15);
      const uint32_t fm = sb + OFF_QS + tr * 128, fx = (lane >> 4) ^ (tr & 7);
      const uint32_t ft = sb + OFF_QT + tr * 32 + (((lane >> 4) ^ (tr >> 2)) & 1) * 16;
      const float g0 = __uint_as_float(lds32(sb + OFF_GATE + (64 * wg + 16 * w + g) * 4));
      const float g1 = __uint_as_float(lds32(sb + OFF_GATE + (64 * wg + 16 * w + 8 + g) * 4));
      const uint32_t ga = pack2(g0, g0), gb = pack2(g1, g1);
      const uint32_t na = pack2(1.f - g0, 1.f - g0), nb = pack2(1.f - g1, 1.f - g1);

      uint32_t qf[20];
      mbar_wait(bars + 8 * B_QF, 0);
      TSM(w == 0 && wg == 0, 99);
#pragma unroll
      for (int j = 0; j < 5; j++) ldsm4(qf + 4 * j, j < 4 ? fm + ((fx ^ (2 * j)) << 4) : ft);
#pragma unroll
      for (int i = 0; i < 20; i++) {
        qf[i] = bmul((i & 1) ? gb : ga, qf[i]);
        asm volatile("" : "+r"(qf[i]));
      }

      wg_wait<0>();
      pin<40>(acc);
      TSM(w == 0, 17 + wg);
      uint32_t pb[20];
#pragma unroll
      for (int j = 0; j < 10; j++) {
        pb[2 * j] = bmul(na, pack2(acc[4 * j], acc[4 * j + 1]));
        pb[2 * j + 1] = bmul(nb, pack2(acc[4 * j + 2], acc[4 * j + 3]));
        asm volatile("" : "+r"(pb[2 * j]), "+r"(pb[2 * j + 1]));
      }
      const uint32_t ya = sb + OFF_YT + wg * 10240 + ((lane >> 4) * 8 + (lane & 7)) * 128 +
                          (((2 * w + (((lane >> 3) & 1) ^ wg)) ^ (lane & 7)) << 4);
      mbar_wait(bars + 8 * B_YFULL, 0);
      TSM(w == 0 && wg == 0, 19);
#pragma unroll
      for (int j = 0; j < 5; j++) {
        uint32_t y[4];
        ldsm4t(y, ya + 2048 * j);
#pragma unroll
        for (int i = 0; i < 4; i++)
          qf[4 * j + i] = bfma(qf[4 * j + i], y[i], pb[4 * j + i]);
      }
#pragma unroll
      for (int j = 0; j < 5; j++) stsm4(j < 4 ? fm + ((fx ^ (2 * j)) << 4) : ft, qf + 4 * j);
      fence_async_smem();
      __syncwarp();
      if (lane == 0) {
        const int row = 64 * wg + 16 * w;
        asm volatile("cp.async.bulk.tensor.2d.global.shared::cta.bulk_group [%0, {%2, %3}], [%1];"
                     ::"l"(&m.om), "r"(sb + OFF_QS + row * 128), "r"(80 * hg), "r"(128 * r + row) : "memory");
        asm volatile("cp.async.bulk.tensor.2d.global.shared::cta.bulk_group [%0, {%2, %3}], [%1];"
                     ::"l"(&m.ot), "r"(sb + OFF_QT + row * 32), "r"(80 * hg + 64), "r"(128 * r + row) : "memory");
        asm volatile("cp.async.bulk.commit_group;\ncp.async.bulk.wait_group.read 0;" ::: "memory");
      }
      TSM(w == 0 || w == 3, 40 + 2 * wg + (w & 1));
    }
  }
}

typedef CUresult (*EncodeFn)(CUtensorMap*, CUtensorMapDataType, cuuint32_t, void*, const cuuint64_t*, const cuuint64_t*,
                             const cuuint32_t*, const cuuint32_t*, CUtensorMapInterleave, CUtensorMapSwizzle,
                             CUtensorMapL2promotion, CUtensorMapFloatOOBfill);

void encode(EncodeFn fn, CUtensorMap* tm, const void* base, int rank, const cuuint64_t* dims, const cuuint64_t* strides,
            const cuuint32_t* box, CUtensorMapSwizzle swz) {
  const cuuint32_t ones[3] = {1, 1, 1};
  fn(tm, CU_TENSOR_MAP_DATA_TYPE_BFLOAT16, rank, const_cast<void*>(base), dims, strides, box, ones,
     CU_TENSOR_MAP_INTERLEAVE_NONE, swz, CU_TENSOR_MAP_L2_PROMOTION_L2_128B, CU_TENSOR_MAP_FLOAT_OOB_FILL_NONE);
}

}

extern "C" void kernel_launch(void* const* d_in, const int* in_sizes, int n_in, void* d_out, int out_size) {
  (void)in_sizes; (void)n_in; (void)out_size;
  Params p;
  p.q = (const __nv_bfloat16*)d_in[0];
  p.k = (const __nv_bfloat16*)d_in[1];
  p.v = (const __nv_bfloat16*)d_in[2];
  p.shift_k = (const __nv_bfloat16*)d_in[3];
  p.ssm_k = (const __nv_bfloat16*)d_in[4];
  p.ssm_D = (const __nv_bfloat16*)d_in[5];
  p.wqkv = (const __nv_bfloat16*)d_in[7];
  p.wo = (const __nv_bfloat16*)d_in[8];
  p.gate_w = (const __nv_bfloat16*)d_in[9];
  p.out = (__nv_bfloat16*)d_out;
  p.zero = 0;

  static EncodeFn fn = nullptr;
  static void *yaddr = nullptr, *oaddr = nullptr;
  if (!fn) {
    cudaDriverEntryPointQueryResult qr;
    void* f = nullptr;
    cudaGetDriverEntryPoint("cuTensorMapEncodeTiled", &f, cudaEnableDefault, &qr);
    fn = (EncodeFn)f;
    cudaGetSymbolAddress(&yaddr, g_U);
    cudaGetSymbolAddress(&oaddr, g_O);
    cudaFuncSetAttribute(fused_kernel, cudaFuncAttributeMaxDynamicSharedMemorySize, SMEM_BYTES);
  }
  Maps m;
  {
    const cuuint64_t dims[3] = {640, 1024, 2}, st[2] = {2560, 1280};
    const cuuint32_t box[3] = {64, 64, 2};
    encode(fn, &m.x, p.q, 3, dims, st, box, CU_TENSOR_MAP_SWIZZLE_128B);
  }
  {
    const cuuint64_t dims[3] = {640, 640, 3}, st[2] = {3840, 1280};
    const cuuint32_t box[3] = {64, 64, 3}, boxt[3] = {16, 64, 3};
    encode(fn, &m.wm, p.wqkv, 3, dims, st, box, CU_TENSOR_MAP_SWIZZLE_128B);
    encode(fn, &m.wt, p.wqkv, 3, dims, st, boxt, CU_TENSOR_MAP_SWIZZLE_32B);
  }
  {
    const cuuint64_t dims[3] = {64, 2048, 10}, st[2] = {1280, 128};
    const cuuint32_t boxk[3] = {64, 35, 1}, boxv[3] = {64, 32, 1};
    encode(fn, &m.k, p.k, 3, dims, st, boxk, CU_TENSOR_MAP_SWIZZLE_128B);
    encode(fn, &m.v, p.v, 3, dims, st, boxv, CU_TENSOR_MAP_SWIZZLE_128B);
  }
  {
    const cuuint64_t dims[3] = {16, 640, 40}, st[2] = {1280, 32};
    const cuuint32_t box[3] = {16, 40, 5};
    encode(fn, &m.wo, p.wo, 3, dims, st, box, CU_TENSOR_MAP_SWIZZLE_32B);
  }
  {
    const cuuint64_t dims[2] = {2048, 640}, st[1] = {U_PITCH * 16};
    const cuuint32_t box[2] = {64, 80};
    encode(fn, &m.y, yaddr, 2, dims, st, box, CU_TENSOR_MAP_SWIZZLE_128B);
    const cuuint64_t dl[2] = {64, DIM * U_PITCH / 8}, dol[2] = {64, NCTA * 160}, sl[1] = {128};
    const cuuint32_t bl[2] = {16, 32}, bol[2] = {16, 160};
    encode(fn, &m.yl, yaddr, 2, dl, sl, bl, CU_TENSOR_MAP_SWIZZLE_NONE);
    encode(fn, &m.ol, oaddr, 2, dol, sl, bol, CU_TENSOR_MAP_SWIZZLE_NONE);
  }
  {
    const cuuint64_t dims[2] = {640, 2048}, st[1] = {1280};
    const cuuint32_t bqm[2] = {64, 128}, bqt[2] = {16, 128}, bom[2] = {64, 16}, bot[2] = {16, 16};
    encode(fn, &m.qm, p.q, 2, dims, st, bqm, CU_TENSOR_MAP_SWIZZLE_128B);
    encode(fn, &m.qt, p.q, 2, dims, st, bqt, CU_TENSOR_MAP_SWIZZLE_32B);
    encode(fn, &m.om, p.out, 2, dims, st, bom, CU_TENSOR_MAP_SWIZZLE_128B);
    encode(fn, &m.ot, p.out, 2, dims, st, bot, CU_TENSOR_MAP_SWIZZLE_32B);
  }
  fused_kernel<<<NCTA, NTHR, SMEM_BYTES>>>(m, p);
}
```

```cpp
#include <cuda.h>
#include <cuda_bf16.h>
#include <cuda_runtime.h>
#include <stdint.h>

namespace {

constexpr int SEQ = 2048, DIM = 640, NCTA = 128, NTHR = 512;

#define KV_KB 2
#define DEV_EXIT 0
#define FENCE_LO 0
#define FENCE_HI 0
#define WB_TRIG B_USIG
#define T_ISSUE 288
#define E_WAIT 1
#define WO_E0 1
#define WO_E1 0
#define T_INIT 448
#define TASK0 0x3
#define TASK1 0x52
#define TASK2 0x41

constexpr uint32_t STAGE_BYTES = 47104, ST_W = 16384, ST_WT = 40960;
constexpr uint32_t O_BYTES = 20480, WO_BYTES = 12800;
constexpr uint32_t OFF_OA = 0;
constexpr uint32_t OFF_QS = 3 * O_BYTES, OFF_QT = OFF_QS + 16384;
constexpr uint32_t OFF_WC = 81920;
constexpr uint32_t OFF_WA = 94720;
constexpr uint32_t OFF_GATE = 145920;
constexpr uint32_t OFF_TT = 146432;
constexpr uint32_t OFF_KVX = 148480;
constexpr uint32_t OFF_CH3 = 163840;
constexpr uint32_t CH_BYTES = 12288, U_BYTES = 4096;
constexpr uint32_t OFF_FT = 225280, OFF_GT = 229376;
constexpr uint32_t OFF_CH0 = 188416;
constexpr uint32_t OFF_KVS = OFF_CH0, KVS_V = 4480, KVS_BYTES = 8576;
constexpr uint32_t OFF_YT = 163840;
constexpr uint32_t OFF_BAR = 231936;
constexpr uint32_t SMEM_BYTES = OFF_BAR + 512;

enum : uint32_t {
  B_EMPTY1 = 0, B_S3 = 3, B_E3 = 4, B_EMPTY2 = 5, B_ATTN = 9, B_P1 = 10,
  B_GATE = 11, B_HA = 12, B_KVD = 13, B_PREP = 14, B_YST = 15,
  B_CVD = 20,
  B_FULL2 = 21, B_U = 29, B_KV = 33, B_HB = 38, B_C34 = 39, B_YRB = 40, B_YFULL = 41, B_EPOCH = 42, B_LAST = 43,
  B_WOP = 44, B_USIG = 45, B_WST = 46, B_QF = 47, B_ORB = 48,
  B_F0 = 49, B_FULL1 = 50
};
constexpr uint32_t OFF_EPOCH = OFF_BAR + 8 * 58, OFF_D = OFF_BAR + 8 * 60;
__device__ __forceinline__ uint32_t off_o(int j) { return j < 4 ? OFF_OA + j * O_BYTES : j < 6 ? OFF_CH0 + (j - 4) * O_BYTES : OFF_OA + (j - 6) * O_BYTES; }
__device__ __forceinline__ uint32_t off_w(int j) { return j < 4 ? OFF_WA + j * WO_BYTES : j == 4 ? OFF_KVX : j == 5 ? OFF_WC : OFF_WA + (j - 6) * WO_BYTES; }
__device__ __forceinline__ int step_src(int hg, int j) { return j == 0 ? hg : j <= hg ? j - 1 : j; }
__device__ __forceinline__ bool tail_first(int hg) { return (hg & 3) == 3; }
__device__ __forceinline__ uint32_t off_ch(int c) { return (c < 3 ? OFF_CH0 : OFF_CH3 - 3 * CH_BYTES) + c * CH_BYTES; }

#define U_PITCH 264
__device__ __align__(1024) uint4 g_U[DIM * U_PITCH];
__device__ __align__(128) uint4 g_O[NCTA * 1280];
__device__ uint4 g_WO[64 * 800];
__device__ uint4 g_halo[NCTA * 2 * 7 * 32];
__device__ __align__(128) float g_gate[SEQ];
__device__ unsigned g_cnt[32 * (1 + 2 * 16 + 8 + NCTA)];
constexpr int C_LAUNCH = 0, C_PREP = 32, C_Y = 32 * 17, C_W = 32 * 33, C_O = 32 * 41;

#define TSM(cond, slot) do { } while (0)
#define TSIF(cond, slot) do { if (__LINE__ >= FENCE_LO && __LINE__ < FENCE_HI) sched_fence(); } while (0)
__device__ __forceinline__ void sched_fence() {
  asm volatile("{\n.reg .pred p;\n.reg .u32 c;\nmov.u32 c, %%clock;\nsetp.eq.u32 p, c, 0;\n@p st.shared.u32 [%0], c;\n}"
               ::"r"(1024 + OFF_EPOCH + 4) : "memory");
}
#define TS(slot) TSIF(true, slot)

struct Params {
  const __nv_bfloat16 *q, *k, *v, *shift_k, *ssm_k, *ssm_D, *wqkv, *wo, *gate_w;
  __nv_bfloat16* out;
  uint32_t zero;
};

constexpr int SPIN_LIMIT = 1 << 17;

__device__ __forceinline__ void mbar_init(uint32_t bar, uint32_t count) {
  asm volatile("mbarrier.init.shared::cta.b64 [%0], %1;" ::"r"(bar), "r"(count) : "memory");
}
__device__ __forceinline__ void mbar_expect_tx(uint32_t bar, uint32_t bytes) {
  asm volatile("mbarrier.arrive.expect_tx.shared::cta.b64 _, [%0], %1;" ::"r"(bar), "r"(bytes) : "memory");
}
__device__ __forceinline__ void mbar_arrive(uint32_t bar) {
  asm volatile("mbarrier.arrive.shared::cta.b64 _, [%0];" ::"r"(bar) : "memory");
}
__device__ __forceinline__ void mbar_wait(uint32_t bar, uint32_t parity) {
  uint32_t ok;
  int spins = 0;
  do {
      asm volatile("{\n.reg .pred p;\nmbarrier.try_wait.parity.shared::cta.b64 p, [%1], %2;\nselp.b32 %0, 1, 0, p;\n}"
                   : "=r"(ok) : "r"(bar), "r"(parity) : "memory");
    if (++spins > SPIN_LIMIT) break;
  } while (!ok);
}
__device__ __forceinline__ unsigned flag_read(const unsigned* p) {
  unsigned v;
  asm volatile("ld.relaxed.gpu.global.u32 %0, [%1];" : "=r"(v) : "l"(p) : "memory");
  return v;
}
__device__ __forceinline__ void flag_poll(const unsigned* p, unsigned target) {
  unsigned v;
  int spins = 0;
  do {
    asm volatile("ld.relaxed.gpu.global.u32 %0, [%1];" : "=r"(v) : "l"(p) : "memory");
    if (++spins > SPIN_LIMIT) break;
  } while ((int)(v - target) < 0);
}
__device__ __forceinline__ void flag_wait(const unsigned* p, unsigned target) {
  flag_poll(p, target);
}
__device__ __forceinline__ void flag_signal(unsigned* p, int n, int lane) {
  if (lane == 0) asm volatile("fence.release.gpu;" ::: "memory");
  __syncwarp();
  if (lane < n) asm volatile("red.relaxed.gpu.global.add.u32 [%0], 1;" ::"l"(p + 32 * lane) : "memory");
}
__device__ __forceinline__ void flag_bump(unsigned* p) {
  asm volatile("red.relaxed.gpu.global.add.u32 [%0], 1;" ::"l"(p) : "memory");
}
__device__ __forceinline__ void fence_async_smem() { asm volatile("fence.proxy.async.shared::cta;" ::: "memory"); }
__device__ __forceinline__ void wg_sync(int id) { asm volatile("bar.sync %0, 128;" ::"r"(id) : "memory"); }

__device__ __forceinline__ void tma_2d(uint32_t dst, const CUtensorMap* tm, int c0, int c1, uint32_t bar) {
  asm volatile("cp.async.bulk.tensor.2d.shared::cluster.global.mbarrier::complete_tx::bytes [%0], [%1, {%3, %4}], [%2];"
               ::"r"(dst), "l"(tm), "r"(bar), "r"(c0), "r"(c1) : "memory");
}
__device__ __forceinline__ void tma_3d(uint32_t dst, const CUtensorMap* tm, int c0, int c1, int c2, uint32_t bar) {
  asm volatile("cp.async.bulk.tensor.3d.shared::cluster.global.mbarrier::complete_tx::bytes [%0], [%1, {%3, %4, %5}], [%2];"
               ::"r"(dst), "l"(tm), "r"(bar), "r"(c0), "r"(c1), "r"(c2) : "memory");
}
__device__ __forceinline__ void bulk_load(uint32_t dst, const void* src, uint32_t bytes, uint32_t bar) {
  asm volatile("cp.async.bulk.shared::cluster.global.mbarrier::complete_tx::bytes [%0], [%1], %2, [%3];"
               ::"r"(dst), "l"(src), "r"(bytes), "r"(bar) : "memory");
}
__device__ __forceinline__ void bulk_store(void* dst, uint32_t src, uint32_t bytes) {
  asm volatile("cp.async.bulk.global.shared::cta.bulk_group [%0], [%1], %2;" ::"l"(dst), "r"(src), "r"(bytes) : "memory");
}
__device__ __forceinline__ void bulk_wait_read() {
  asm volatile("cp.async.bulk.commit_group;\ncp.async.bulk.wait_group.read 0;" ::: "memory");
}

__device__ __forceinline__ void publish(void* dst, uint32_t src, uint32_t bytes) {
  bulk_store(dst, src, bytes);
  bulk_wait_read();
}

__device__ __forceinline__ void wg_fence() { asm volatile("wgmma.fence.sync.aligned;" ::: "memory"); }
__device__ __forceinline__ void wg_commit() { asm volatile("wgmma.commit_group.sync.aligned;" ::: "memory"); }
template <int N> __device__ __forceinline__ void wg_wait() { asm volatile("wgmma.wait_group.sync.aligned %0;" ::"n"(N) : "memory"); }
__device__ __forceinline__ uint32_t desc_lo(uint32_t addr, uint32_t lbo) { return ((addr & 0x3FFFF) >> 4) | ((lbo >> 4) << 16); }
constexpr uint32_t desc_hi(uint32_t sbo, uint32_t swz) { return (sbo >> 4) | (swz << 30); }
constexpr uint32_t HI_SW128 = desc_hi(1024, 1), HI_SW64 = desc_hi(512, 2), HI_SW32 = desc_hi(256, 3), HI_NONE = desc_hi(128, 0);
template <int N> __device__ __forceinline__ void pin(float* d) {
#pragma unroll
  for (int i = 0; i < N; i++) asm volatile("" : "+f"(d[i])::"memory");
}

__device__ __forceinline__ uint32_t lds32(uint32_t a) {
  uint32_t v;
  asm volatile("ld.volatile.shared.u32 %0, [%1];" : "=r"(v) : "r"(a) : "memory");
  return v;
}
__device__ __forceinline__ uint2 ldg64(const void* a) {
  uint2 v;
  asm volatile("ld.global.nc.v2.u32 {%0, %1}, [%2];" : "=r"(v.x), "=r"(v.y) : "l"(a) : "memory");
  return v;
}
__device__ __forceinline__ void ldsm4(uint32_t* r, uint32_t a) {
  asm volatile("ldmatrix.sync.aligned.m8n8.x4.shared.b16 {%0, %1, %2, %3}, [%4];"
               : "=r"(r[0]), "=r"(r[1]), "=r"(r[2]), "=r"(r[3]) : "r"(a) : "memory");
}
__device__ __forceinline__ void ldsm4t(uint32_t* r, uint32_t a) {
  asm volatile("ldmatrix.sync.aligned.m8n8.x4.trans.shared.b16 {%0, %1, %2, %3}, [%4];"
               : "=r"(r[0]), "=r"(r[1]), "=r"(r[2]), "=r"(r[3]) : "r"(a) : "memory");
}
__device__ __forceinline__ uint2 lds64(uint32_t a) {
  uint2 v;
  asm volatile("ld.shared.v2.u32 {%0, %1}, [%2];" : "=r"(v.x), "=r"(v.y) : "r"(a) : "memory");
  return v;
}
__device__ __forceinline__ uint4 lds128(uint32_t a) {
  uint4 v;
  asm volatile("ld.shared.v4.u32 {%0, %1, %2, %3}, [%4];" : "=r"(v.x), "=r"(v.y), "=r"(v.z), "=r"(v.w) : "r"(a) : "memory");
  return v;
}
__device__ __forceinline__ void sts128(uint32_t a, uint32_t x, uint32_t y, uint32_t z, uint32_t w) {
  asm volatile("st.shared.v4.u32 [%0], {%1, %2, %3, %4};" ::"r"(a), "r"(x), "r"(y), "r"(z), "r"(w) : "memory");
}
__device__ __forceinline__ void stsm4(uint32_t a, const uint32_t* r) {
  asm volatile("stmatrix.sync.aligned.m8n8.x4.shared.b16 [%0], {%1, %2, %3, %4};" ::"r"(a), "r"(r[0]), "r"(r[1]), "r"(r[2]), "r"(r[3]) : "memory");
}
__device__ __forceinline__ uint32_t pack2(float lo, float hi) {
  uint32_t r;
  asm("cvt.rn.bf16x2.f32 %0, %1, %2;" : "=r"(r) : "f"(hi), "f"(lo));
  return r;
}
__device__ __forceinline__ uint32_t movm(uint32_t a) {
  uint32_t d;
  asm volatile("movmatrix.sync.aligned.m8n8.trans.b16 %0, %1;" : "=r"(d) : "r"(a));
  return d;
}
__device__ __forceinline__ uint32_t bmul(uint32_t a, uint32_t b) {
  uint32_t d;
  asm("mul.rn.bf16x2 %0, %1, %2;" : "=r"(d) : "r"(a), "r"(b));
  return d;
}
__device__ __forceinline__ uint32_t badd(uint32_t a, uint32_t b) {
  uint32_t d;
  asm("add.rn.bf16x2 %0, %1, %2;" : "=r"(d) : "r"(a), "r"(b));
  return d;
}
__device__ __forceinline__ uint32_t bfma(uint32_t a, uint32_t b, uint32_t c) {
  uint32_t d;
  asm("fma.rn.bf16x2 %0, %1, %2, %3;" : "=r"(d) : "r"(a), "r"(b), "r"(c));
  return d;
}
__device__ __forceinline__ float bf_lo(uint32_t x) { return __uint_as_float(x << 16); }
__device__ __forceinline__ float bf_hi(uint32_t x) { return __uint_as_float(x & 0xFFFF0000u); }
__device__ __forceinline__ float ex2(float x) {
  float y;
  asm("ex2.approx.ftz.f32 %0, %1;" : "=f"(y) : "f"(x));
  return y;
}
__device__ __forceinline__ float rcp(float x) {
  float y;
  asm("rcp.approx.ftz.f32 %0, %1;" : "=f"(y) : "f"(x));
  return y;
}
__device__ __forceinline__ void mma16816(float* d, uint32_t a0, uint32_t a1, uint32_t a2, uint32_t a3, uint32_t b0, uint32_t b1) {
  asm volatile("mma.sync.aligned.m16n8k16.row.col.f32.bf16.bf16.f32 {%0, %1, %2, %3}, {%4, %5, %6, %7}, {%8, %9}, {%0, %1, %2, %3};"
               : "+f"(d[0]), "+f"(d[1]), "+f"(d[2]), "+f"(d[3])
               : "r"(a0), "r"(a1), "r"(a2), "r"(a3), "r"(b0), "r"(b1));
}
__device__ __forceinline__ void mma1688(float* d, uint32_t a0, uint32_t a1, uint32_t b0) {
  asm volatile("mma.sync.aligned.m16n8k8.row.col.f32.bf16.bf16.f32 {%0, %1, %2, %3}, {%4, %5}, {%6}, {%0, %1, %2, %3};"
               : "+f"(d[0]), "+f"(d[1]), "+f"(d[2]), "+f"(d[3])
               : "r"(a0), "r"(a1), "r"(b0));
}

template <int N> struct WgRS;
template <int N> struct WgSST;
template <> struct WgRS<32> {
  template <uint32_t HB>
  static __device__ __forceinline__ void mma(float* d, const uint32_t* a, uint32_t db) {
    asm volatile("{\n.reg .pred p;\n.reg .b64 db;\nsetp.ne.b32 p, %22, 0;\n"
      "mov.b64 db, {%20, %21};\n"
      "wgmma.mma_async.sync.aligned.m64n32k16.f32.bf16.bf16 {"
      "%0, %1, %2, %3, %4, %5, %6, %7, %8, %9, %10, %11, %12, %13, %14, %15"
      "}, {%16, %17, %18, %19}, db, p, 1, 1, 1;\n}\n"
      : "+f"(d[0]), "+f"(d[1]), "+f"(d[2]), "+f"(d[3]), "+f"(d[4]), "+f"(d[5]), "+f"(d[6]), "+f"(d[7]),
        "+f"(d[8]), "+f"(d[9]), "+f"(d[10]), "+f"(d[11]), "+f"(d[12]), "+f"(d[13]), "+f"(d[14]), "+f"(d[15])
      : "r"(a[0]), "r"(a[1]), "r"(a[2]), "r"(a[3]), "r"(db), "n"(HB), "n"(1));
  }
  template <uint32_t HB>
  static __device__ __forceinline__ void set(float* d, const uint32_t* a, uint32_t db) {
    asm volatile("{\n.reg .pred p;\n.reg .b64 db;\nsetp.ne.b32 p, %22, 0;\n"
      "mov.b64 db, {%20, %21};\n"
      "wgmma.mma_async.sync.aligned.m64n32k16.f32.bf16.bf16 {"
      "%0, %1, %2, %3, %4, %5, %6, %7, %8, %9, %10, %11, %12, %13, %14, %15"
      "}, {%16, %17, %18, %19}, db, p, 1, 1, 1;\n}\n"
      : "=f"(d[0]), "=f"(d[1]), "=f"(d[2]), "=f"(d[3]), "=f"(d[4]), "=f"(d[5]), "=f"(d[6]), "=f"(d[7]),
        "=f"(d[8]), "=f"(d[9]), "=f"(d[10]), "=f"(d[11]), "=f"(d[12]), "=f"(d[13]), "=f"(d[14]), "=f"(d[15])
      : "r"(a[0]), "r"(a[1]), "r"(a[2]), "r"(a[3]), "r"(db), "n"(HB), "n"(0));
  }
};
template <> struct WgRS<64> {
  template <uint32_t HB>
  static __device__ __forceinline__ void mma(float* d, const uint32_t* a, uint32_t db) {
    asm volatile("{\n.reg .pred p;\n.reg .b64 db;\nsetp.ne.b32 p, %38, 0;\n"
      "mov.b64 db, {%36, %37};\n"
      "wgmma.mma_async.sync.aligned.m64n64k16.f32.bf16.bf16 {"
      "%0, %1, %2, %3, %4, %5, %6, %7, %8, %9, %10, %11, %12, %13, %14, %15, "
      "%16, %17, %18, %19, %20, %21, %22, %23, %24, %25, %26, %27, %28, %29, %30, %31"
      "}, {%32, %33, %34, %35}, db, p, 1, 1, 1;\n}\n"
      : "+f"(d[0]), "+f"(d[1]), "+f"(d[2]), "+f"(d[3]), "+f"(d[4]), "+f"(d[5]), "+f"(d[6]), "+f"(d[7]),
        "+f"(d[8]), "+f"(d[9]), "+f"(d[10]), "+f"(d[11]), "+f"(d[12]), "+f"(d[13]), "+f"(d[14]), "+f"(d[15]),
        "+f"(d[16]), "+f"(d[17]), "+f"(d[18]), "+f"(d[19]), "+f"(d[20]), "+f"(d[21]), "+f"(d[22]), "+f"(d[23]),
        "+f"(d[24]), "+f"(d[25]), "+f"(d[26]), "+f"(d[27]), "+f"(d[28]), "+f"(d[29]), "+f"(d[30]), "+f"(d[31])
      : "r"(a[0]), "r"(a[1]), "r"(a[2]), "r"(a[3]), "r"(db), "n"(HB), "n"(1));
  }
  template <uint32_t HB>
  static __device__ __forceinline__ void set(float* d, const uint32_t* a, uint32_t db) {
    asm volatile("{\n.reg .pred p;\n.reg .b64 db;\nsetp.ne.b32 p, %38, 0;\n"
      "mov.b64 db, {%36, %37};\n"
      "wgmma.mma_async.sync.aligned.m64n64k16.f32.bf16.bf16 {"
      "%0, %1, %2, %3, %4, %5, %6, %7, %8, %9, %10, %11, %12, %13, %14, %15, "
      "%16, %17, %18, %19, %20, %21, %22, %23, %24, %25, %26, %27, %28, %29, %30, %31"
      "}, {%32, %33, %34, %35}, db, p, 1, 1, 1;\n}\n"
      : "=f"(d[0]), "=f"(d[1]), "=f"(d[2]), "=f"(d[3]), "=f"(d[4]), "=f"(d[5]), "=f"(d[6]), "=f"(d[7]),
        "=f"(d[8]), "=f"(d[9]), "=f"(d[10]), "=f"(d[11]), "=f"(d[12]), "=f"(d[13]), "=f"(d[14]), "=f"(d[15]),
        "=f"(d[16]), "=f"(d[17]), "=f"(d[18]), "=f"(d[19]), "=f"(d[20]), "=f"(d[21]), "=f"(d[22]), "=f"(d[23]),
        "=f"(d[24]), "=f"(d[25]), "=f"(d[26]), "=f"(d[27]), "=f"(d[28]), "=f"(d[29]), "=f"(d[30]), "=f"(d[31])
      : "r"(a[0]), "r"(a[1]), "r"(a[2]), "r"(a[3]), "r"(db), "n"(HB), "n"(0));
  }
};
template <> struct WgSST<48> {
  template <uint32_t HA, uint32_t HB>
  static __device__ __forceinline__ void mma(float* d, uint32_t da, uint32_t db, int sc) {
    asm volatile("{\n.reg .pred p;\n.reg .b64 da, db;\nsetp.ne.b32 p, %28, 0;\n"
      "mov.b64 da, {%24, %25};\nmov.b64 db, {%26, %27};\n"
      "wgmma.mma_async.sync.aligned.m64n48k16.f32.bf16.bf16 {"
      "%0, %1, %2, %3, %4, %5, %6, %7, %8, %9, %10, %11, %12, %13, %14, %15, "
      "%16, %17, %18, %19, %20, %21, %22, %23"
      "}, da, db, p, 1, 1, 0, 1;\n}\n"
      : "+f"(d[0]), "+f"(d[1]), "+f"(d[2]), "+f"(d[3]), "+f"(d[4]), "+f"(d[5]), "+f"(d[6]), "+f"(d[7]),
        "+f"(d[8]), "+f"(d[9]), "+f"(d[10]), "+f"(d[11]), "+f"(d[12]), "+f"(d[13]), "+f"(d[14]), "+f"(d[15]),
        "+f"(d[16]), "+f"(d[17]), "+f"(d[18]), "+f"(d[19]), "+f"(d[20]), "+f"(d[21]), "+f"(d[22]), "+f"(d[23])
      : "r"(da), "n"(HA), "r"(db), "n"(HB), "r"(sc));
  }
};
template <> struct WgSST<80> {
  template <uint32_t HA, uint32_t HB>
  static __device__ __forceinline__ void mma(float* d, uint32_t da, uint32_t db, int sc) {
    asm volatile("{\n.reg .pred p;\n.reg .b64 da, db;\nsetp.ne.b32 p, %44, 0;\n"
      "mov.b64 da, {%40, %41};\nmov.b64 db, {%42, %43};\n"
      "wgmma.mma_async.sync.aligned.m64n80k16.f32.bf16.bf16 {"
      "%0, %1, %2, %3, %4, %5, %6, %7, %8, %9, %10, %11, %12, %13, %14, %15, "
      "%16, %17, %18, %19, %20, %21, %22, %23, %24, %25, %26, %27, %28, %29, %30, %31, "
      "%32, %33, %34, %35, %36, %37, %38, %39"
      "}, da, db, p, 1, 1, 0, 1;\n}\n"
      : "+f"(d[0]), "+f"(d[1]), "+f"(d[2]), "+f"(d[3]), "+f"(d[4]), "+f"(d[5]), "+f"(d[6]), "+f"(d[7]),
        "+f"(d[8]), "+f"(d[9]), "+f"(d[10]), "+f"(d[11]), "+f"(d[12]), "+f"(d[13]), "+f"(d[14]), "+f"(d[15]),
        "+f"(d[16]), "+f"(d[17]), "+f"(d[18]), "+f"(d[19]), "+f"(d[20]), "+f"(d[21]), "+f"(d[22]), "+f"(d[23]),
        "+f"(d[24]), "+f"(d[25]), "+f"(d[26]), "+f"(d[27]), "+f"(d[28]), "+f"(d[29]), "+f"(d[30]), "+f"(d[31]),
        "+f"(d[32]), "+f"(d[33]), "+f"(d[34]), "+f"(d[35]), "+f"(d[36]), "+f"(d[37]), "+f"(d[38]), "+f"(d[39])
      : "r"(da), "n"(HA), "r"(db), "n"(HB), "r"(sc));
  }
};
template <> struct WgSST<192> {
  template <uint32_t HA, uint32_t HB>
  static __device__ __forceinline__ void mma(float* d, uint32_t da, uint32_t db, int sc) {
    asm volatile("{\n.reg .pred p;\n.reg .b64 da, db;\nsetp.ne.b32 p, %100, 0;\n"
      "mov.b64 da, {%96, %97};\nmov.b64 db, {%98, %99};\n"
      "wgmma.mma_async.sync.aligned.m64n192k16.f32.bf16.bf16 {"
      "%0, %1, %2, %3, %4, %5, %6, %7, %8, %9, %10, %11, %12, %13, %14, %15, "
      "%16, %17, %18, %19, %20, %21, %22, %23, %24, %25, %26, %27, %28, %29, %30, %31, "
      "%32, %33, %34, %35, %36, %37, %38, %39, %40, %41, %42, %43, %44, %45, %46, %47, "
      "%48, %49, %50, %51, %52, %53, %54, %55, %56, %57, %58, %59, %60, %61, %62, %63, "
      "%64, %65, %66, %67, %68, %69, %70, %71, %72, %73, %74, %75, %76, %77, %78, %79, "
      "%80, %81, %82, %83, %84, %85, %86, %87, %88, %89, %90, %91, %92, %93, %94, %95"
      "}, da, db, p, 1, 1, 0, 1;\n}\n"
      : "+f"(d[0]), "+f"(d[1]), "+f"(d[2]), "+f"(d[3]), "+f"(d[4]), "+f"(d[5]), "+f"(d[6]), "+f"(d[7]),
        "+f"(d[8]), "+f"(d[9]), "+f"(d[10]), "+f"(d[11]), "+f"(d[12]), "+f"(d[13]), "+f"(d[14]), "+f"(d[15]),
        "+f"(d[16]), "+f"(d[17]), "+f"(d[18]), "+f"(d[19]), "+f"(d[20]), "+f"(d[21]), "+f"(d[22]), "+f"(d[23]),
        "+f"(d[24]), "+f"(d[25]), "+f"(d[26]), "+f"(d[27]), "+f"(d[28]), "+f"(d[29]), "+f"(d[30]), "+f"(d[31]),
        "+f"(d[32]), "+f"(d[33]), "+f"(d[34]), "+f"(d[35]), "+f"(d[36]), "+f"(d[37]), "+f"(d[38]), "+f"(d[39]),
        "+f"(d[40]), "+f"(d[41]), "+f"(d[42]), "+f"(d[43]), "+f"(d[44]), "+f"(d[45]), "+f"(d[46]), "+f"(d[47]),
        "+f"(d[48]), "+f"(d[49]), "+f"(d[50]), "+f"(d[51]), "+f"(d[52]), "+f"(d[53]), "+f"(d[54]), "+f"(d[55]),
        "+f"(d[56]), "+f"(d[57]), "+f"(d[58]), "+f"(d[59]), "+f"(d[60]), "+f"(d[61]), "+f"(d[62]), "+f"(d[63]),
        "+f"(d[64]), "+f"(d[65]), "+f"(d[66]), "+f"(d[67]), "+f"(d[68]), "+f"(d[69]), "+f"(d[70]), "+f"(d[71]),
        "+f"(d[72]), "+f"(d[73]), "+f"(d[74]), "+f"(d[75]), "+f"(d[76]), "+f"(d[77]), "+f"(d[78]), "+f"(d[79]),
        "+f"(d[80]), "+f"(d[81]), "+f"(d[82]), "+f"(d[83]), "+f"(d[84]), "+f"(d[85]), "+f"(d[86]), "+f"(d[87]),
        "+f"(d[88]), "+f"(d[89]), "+f"(d[90]), "+f"(d[91]), "+f"(d[92]), "+f"(d[93]), "+f"(d[94]), "+f"(d[95])
      : "r"(da), "n"(HA), "r"(db), "n"(HB), "r"(sc));
  }
};

struct FftConst {
  uint32_t f[2][4], fi[4][4];
  uint32_t ta[2][2], tb[2][2];
};
__device__ __forceinline__ void cis(int m, float scale, float& c, float& s) {
  const float a = (float)m * (-6.283185307179586f * scale);
  c = __cosf(a);
  s = __sinf(a);
}
__device__ __forceinline__ void fft_tables(uint32_t (&v)[12], int tw) {
  const int row = tw >> 2, ch = tw & 3;
#pragma unroll
  for (int i = 0; i < 4; i++) {
    float c[2], s[2], x[2];
#pragma unroll
    for (int e = 0; e < 2; e++) {
      cis((((32 * (8 * ch + 2 * i + e) + 15) * (4 * row - 63) + 2048) & 4095) - 2048, 1.f / 4096, c[e], s[e]);
      float gc, gs;
      cis((((row & 15) * (8 * (ch & 1) + 2 * i + e) + 8) & 15) - 8, 1.f / 16, gc, gs);
      x[e] = (row >> 4) == (ch >> 1) ? gc : (ch >> 1) ? gs : -gs;
    }
    v[i] = pack2(c[0] * 0.125f, c[1] * 0.125f);
    v[4 + i] = pack2(s[0] * 0.125f, s[1] * 0.125f);
    v[8 + i] = pack2(x[0], x[1]);
  }
#pragma unroll
  for (int i = 0; i < 12; i++) asm volatile("" : "+r"(v[i]));
}
__device__ __forceinline__ void fft_tables_store(const uint32_t (&v)[12], uint32_t sb, int tw) {
  const int row = tw >> 2;
  const uint32_t x = ((tw ^ (row >> 1)) & 3) << 4, a = sb + OFF_FT + (16 * (row >> 3) + (row & 7)) * 64 + x;
  sts128(a, v[0], v[1], v[2], v[3]);
  sts128(a + 512, v[4], v[5], v[6], v[7]);
  sts128(sb + OFF_GT + row * 64 + x, v[8], v[9], v[10], v[11]);
}
__device__ __forceinline__ void fft_twiddles(uint32_t (&v)[2], int tw) {
  float a[2], s[2];
#pragma unroll
  for (int i = 0; i < 2; i++) {
    float c;
    cis((2 * (2 * (tw & 3) + i) - 15) * (4 * (tw >> 2) - 63), 1.f / 4096, c, s[i]);
    a[i] = __fdividef(-s[i], 1.f + c);
  }
  v[0] = pack2(a[0], a[1]);
  v[1] = pack2(s[0], s[1]);
  asm volatile("" : "+r"(v[0]), "+r"(v[1]));
}
__device__ __forceinline__ void fft_matrices(FftConst& k, uint32_t sb, int w, int lane) {
  const uint32_t x = (lane >> 1) & 3;
  const uint2 t0 = lds64(sb + OFF_TT + 256 * w + 8 * lane), t1 = lds64(sb + OFF_TT + 256 * w + 8 * (lane ^ 3));
  k.ta[0][0] = t0.x;
  k.tb[0][0] = t0.y;
  k.ta[1][1] = __byte_perm(t1.x, 0, 0x1032);
  k.tb[1][1] = __byte_perm(t1.y, 0, 0x1032);
#pragma unroll
  for (int j = 0; j < 2; j++) {
    k.ta[1 - j][j] = k.ta[j][j] ^ 0x80008000u;
    k.tb[1 - j][j] = k.tb[j][j] ^ 0x80008000u;
    asm volatile("" : "+r"(k.ta[0][j]), "+r"(k.tb[0][j]), "+r"(k.ta[1][j]), "+r"(k.tb[1][j]));
  }
#pragma unroll
  for (int i = 0; i < 2; i++) {
    ldsm4(k.f[i], sb + OFF_FT + (16 * w + (lane & 15)) * 64 + (((2 * i + (lane >> 4)) ^ x) << 4));
    ldsm4t(k.fi[i], sb + OFF_FT + (32 * i + lane) * 64 + ((w ^ x) << 4));
#pragma unroll
    for (int j = 0; j < 4; j++) {
      k.fi[2 + i][j] = (j & 1) ? k.fi[i][j - 1] ^ 0x80008000u : k.fi[i][j + 1];
      asm volatile("" : "+r"(k.fi[2 + i][j]));
    }
  }
}
__device__ __forceinline__ void rot(uint32_t& x, uint32_t& y, uint32_t a, uint32_t b) {
  x = bfma(a, y, x);
  y = bfma(b, x, y);
  x = bfma(a, y, x);
}
__device__ __forceinline__ void twiddle_fwd(uint32_t (&a)[4][4], float* d, const FftConst& k) {
#pragma unroll
  for (int q = 0; q < 4; q++)
#pragma unroll
    for (int j = 0; j < 2; j++) {
      const float* x = d + 8 * q + 4 * j;
      uint32_t re = pack2(x[0], x[1]), im = pack2(x[2], x[3]);
      rot(re, im, k.ta[0][j], k.tb[0][j]);
      a[q & 2][2 * j + (q & 1)] = re;
      a[(q & 2) + 1][2 * j + (q & 1)] = im;
    }
}
__device__ __forceinline__ void g_step(float* d, const uint32_t (&a)[4][4], uint32_t dre, uint32_t dim) {
  WgRS<32>::set<HI_SW64>(d, a[0], dre);
  WgRS<32>::set<HI_SW64>(d + 16, a[2], dre);
  WgRS<32>::mma<HI_SW64>(d, a[1], dim);
  WgRS<32>::mma<HI_SW64>(d + 16, a[3], dim);
  wg_commit();
}

__device__ __forceinline__ void products(uint32_t (&a)[4][4], const float* H, const float* U, int p) {
#pragma unroll
  for (int j = 0; j < 2; j++)
#pragma unroll
    for (int m = 2 * p; m < 2 * p + 2; m++) {
      float pr[2], pi[2];
#pragma unroll
      for (int x = 0; x < 2; x++)
#pragma unroll
        for (int q = 0; q <= m; q++) {
          const int ih = 16 * (q >> 1) + 2 * (q & 1) + 4 * j + x, iu = 16 * ((m - q) >> 1) + 2 * ((m - q) & 1) + 4 * j + x;
          pr[x] = q ? fmaf(H[ih], U[iu], pr[x]) : H[ih] * U[iu];
          pi[x] = q ? fmaf(H[ih], U[iu + 8], pi[x]) : H[ih] * U[iu + 8];
          pr[x] = fmaf(-H[ih + 8], U[iu + 8], pr[x]);
          pi[x] = fmaf(H[ih + 8], U[iu], pi[x]);
        }
      a[m & 2][2 * j + (m & 1)] = pack2(pr[0], pr[1]);
      a[(m & 2) + 1][2 * j + (m & 1)] = pack2(pi[0], pi[1]);
    }
}

__device__ __forceinline__ void conv_channel(const FftConst& k, uint32_t sb, int c, int wg, int w, int lane) {
  const uint32_t cb = sb + off_ch(c), bars = sb + OFF_BAR;
  const uint32_t du = desc_lo(cb, 1024), dg = desc_lo(sb + OFF_GT, 16), dz = desc_lo(cb + U_BYTES, 16);
  float U[32], H[32];
  uint32_t a[4][4], e[4][4];
  const float dv = __uint_as_float(lds32(sb + OFF_D + 4 * c));
  wg_fence();
  WgRS<64>::set<HI_SW32>(H, k.f[0], du + 256);
  WgRS<64>::mma<HI_SW32>(H, k.f[1], du + 256 + 32);
  wg_commit();
  wg_wait<0>();
  pin<32>(H);
  twiddle_fwd(a, H, k);
  mbar_wait(bars + 8 * (B_U + (c < 3 ? c : 3)), 0);
  TSM(w == 0 && c < 3, 7 + wg);
  wg_fence();
  WgRS<64>::set<HI_SW32>(U, k.f[0], du);
  WgRS<64>::mma<HI_SW32>(U, k.f[1], du + 32);
  wg_commit();
  g_step(H, a, dg, dg + 64);
  wg_wait<1>();
  pin<32>(U);
  twiddle_fwd(e, U, k);
  wg_fence();
  g_step(U, e, dg, dg + 64);
  wg_wait<0>();
  pin<32>(U);
  pin<32>(H);
#pragma unroll
  for (int j = 0; j < 4; j++) H[4 * (j >> 1) + (j & 1)] += dv;
  float V[32];
#pragma unroll
  for (int p = 0; p < 2; p++) {
    products(a, H, U, p);
    wg_fence();
    WgRS<32>::set<HI_SW64>(V + 16 * p, a[2 * p], dg + 64);
    WgRS<32>::mma<HI_SW64>(V + 16 * p, a[2 * p + 1], dg);
    wg_commit();
  }
  const uint32_t za = cb + U_BYTES + (8 * w + (lane & 7)) * 128 + (((lane >> 3) ^ (lane & 7)) << 4);
  const uint32_t ya = cb + (lane >> 4) * 1024 + (8 * w + (lane & 7)) * 32 + ((((lane >> 3) ^ (lane >> 2)) & 1) << 4);
  wg_sync(1 + wg);
#pragma unroll
  for (int p = 0; p < 2; p++) {
    if (p == 0) wg_wait<1>();
    else wg_wait<0>();
    pin<16>(V + 16 * p);
#pragma unroll
    for (int i = 0; i < 4; i++) {
      const int j = i & 1;
      const float* x = V + 16 * p + 4 * j + (i & 2);
      e[p][i] = pack2(x[8], x[9]);
      e[2 + p][i] = pack2(x[0], x[1]);
      rot(e[p][i], e[2 + p][i], k.ta[1][j], k.tb[1][j]);
    }
    stsm4(za ^ (64 * p), e[p]);
    stsm4((za ^ (64 * p)) + 4096, e[2 + p]);
  }
  fence_async_smem();
  wg_sync(1 + wg);
  wg_fence();
  WgRS<64>::set<HI_SW128>(H, k.fi[0], dz);
#pragma unroll
  for (int ks = 1; ks < 4; ks++) WgRS<64>::mma<HI_SW128>(H, k.fi[ks], dz + 128 * ks);
  wg_commit();
  wg_wait<0>();
  pin<32>(H);
  if (lane == 0) mbar_arrive(bars + 8 * B_CVD);
  TSIF(w == 0, 88 + c);
#pragma unroll
  for (int j = 0; j < 8; j++)
    a[j >> 2][j & 3] = j < 2 ? pack2(H[4 * j], H[4 * j + 1]) : pack2(H[4 * j] + H[4 * j - 6], H[4 * j + 1] + H[4 * j - 5]);
  stsm4(ya, a[0]);
  stsm4(ya + 2048, a[1]);
  fence_async_smem();
  __syncwarp();
}

__device__ __forceinline__ void prep_slab(uint4* res, const uint2* sw, uint32_t sb, int slab, int w, int lane) {
  const int t = lane & 3, tp = (lane & 7) >> 1, pos = 8 * tp + 2 * (((lane >> 3) + tp) & 3) + (lane & 1);
  const uint32_t base = sb + OFF_KVS + slab * KVS_BYTES + pos * 128;
  uint32_t kk[2][4][4], vv[2][4];
  mbar_wait(sb + OFF_BAR + 8 * (B_KV + slab), 0);
#pragma unroll
  for (int h = 0; h < 2; h++) {
#pragma unroll
    for (int j = 0; j < 4; j++) {
      const uint32_t a = base + 128 * j;
      ldsm4t(kk[h][j], a + (((w + 4 * h) ^ ((a >> 7) & 7)) << 4));
    }
    const uint32_t a = base + KVS_V;
    ldsm4t(vv[h], a + (((w + 4 * h) ^ ((a >> 7) & 7)) << 4));
  }
#pragma unroll
  for (int h = 0; h < 2; h++) {
    uint32_t (&k)[4][4] = kk[h];
    uint32_t (&v)[4] = vv[h];
    const uint32_t w0 = __byte_perm(sw[h].x, 0, 0x1010), w1 = __byte_perm(sw[h].x, 0, 0x3232);
    const uint32_t w2 = __byte_perm(sw[h].y, 0, 0x1010), w3 = __byte_perm(sw[h].y, 0, 0x3232);
#pragma unroll
    for (int m = 0; m < 4; m++)
      v[m] = bmul(badd(badd(badd(bmul(k[0][m], w3), bmul(k[1][m], w2)), bmul(k[2][m], w1)), bmul(k[3][m], w0)), v[m]);
    uint32_t a[4];
#pragma unroll
    for (int m = 0; m < 4; m++) a[m] = (t & 1) ? v[(m + 3) & 3] : v[m];
    res[h] = (t & 2) ? make_uint4(a[2], a[3], a[0], a[1]) : make_uint4(a[0], a[1], a[2], a[3]);
  }
}

__device__ __forceinline__ void prep_gate(const Params& p, uint32_t sb, int b, int w, int lane) {
  uint2 gw[5], x[4][5];
#pragma unroll
  for (int j = 0; j < 5; j++) gw[j] = ldg64(reinterpret_cast<const uint2*>(p.gate_w) + lane + 32 * j);
#pragma unroll
  for (int i = 0; i < 4; i++)
#pragma unroll
    for (int j = 0; j < 5; j++)
      x[i][j] = ldg64(reinterpret_cast<const uint2*>(p.q) + (16 * b + 4 * w + i) * (DIM / 4) + lane + 32 * j);
  float s[4];
#pragma unroll
  for (int i = 0; i < 4; i++) {
    s[i] = 0.f;
#pragma unroll
    for (int j = 0; j < 5; j++) {
      const uint32_t m0 = bmul(x[i][j].x, gw[j].x), m1 = bmul(x[i][j].y, gw[j].y);
      s[i] += (bf_lo(m0) + bf_hi(m0)) + (bf_lo(m1) + bf_hi(m1));
    }
  }
  const bool h = lane & 16, q = lane & 8;
  const float a = (h ? s[2] : s[0]) + __shfl_xor_sync(0xffffffffu, h ? s[0] : s[2], 16);
  const float c = (h ? s[3] : s[1]) + __shfl_xor_sync(0xffffffffu, h ? s[1] : s[3], 16);
  float z = (q ? c : a) + __shfl_xor_sync(0xffffffffu, q ? a : c, 8);
#pragma unroll
  for (int o = 4; o > 0; o >>= 1) z += __shfl_xor_sync(0xffffffffu, z, o);
  z = bf_lo(pack2(z, 0.f));
  z = bf_lo(pack2(__fdividef(1.f, 1.f + __expf(-z)), 0.f));
  mbar_wait(sb + OFF_BAR + 8 * B_S3, 0);
  if ((lane & 7) == 0) asm volatile("st.shared.f32 [%0], %1;" ::"r"(sb + OFF_GATE + 64 * (b & 7) + 16 * w + (lane >> 1)), "f"(z) : "memory");
  fence_async_smem();
}

__device__ __forceinline__ uint32_t bmax(uint32_t a, uint32_t b) {
  uint32_t d;
  asm("max.bf16x2 %0, %1, %2;" : "=r"(d) : "r"(a), "r"(b));
  return d;
}
__device__ __forceinline__ void softmax_two(const float (&l)[2][2], uint32_t& p0, uint32_t& p1) {
  constexpr float kScale = 0.22360679774997896f, kLog2e = 1.4426950408889634f;
  const uint32_t r0 = pack2(l[0][0], l[1][0]), r1 = pack2(l[0][1], l[1][1]);
  const uint32_t x0 = pack2(bf_lo(r0) * kScale, bf_hi(r0) * kScale), x1 = pack2(bf_lo(r1) * kScale, bf_hi(r1) * kScale);
  uint32_t m = bmax(x0, x1);
  m = bmax(m, __shfl_xor_sync(0xffffffffu, m, 1));
  m = bmax(m, __shfl_xor_sync(0xffffffffu, m, 2));
  const float m0 = bf_lo(m) * kLog2e, m1 = bf_hi(m) * kLog2e;
  p0 = pack2(ex2(bf_lo(x0) * kLog2e - m0), ex2(bf_lo(x1) * kLog2e - m0));
  p1 = pack2(ex2(bf_hi(x0) * kLog2e - m1), ex2(bf_hi(x1) * kLog2e - m1));
}

__device__ __forceinline__ void halo_read(uint32_t (&kpv)[10], uint32_t (&vpv)[10], uint32_t (&tg)[7], const uint4* hp) {
#pragma unroll
  for (int j = 0; j < 7; j++) {
    uint32_t x0, x1, x2;
    asm volatile("ld.relaxed.gpu.global.v4.u32 {%0, %1, %2, %3}, [%4];"
                 : "=r"(x0), "=r"(x1), "=r"(x2), "=r"(tg[j]) : "l"(hp + 32 * j) : "memory");
    if (j < 4) kpv[3 * j] = x0; else vpv[3 * j - 10] = x0;
    if (j < 3) kpv[3 * j + 1] = x1; else vpv[3 * j - 9] = x1;
    if (j < 3) kpv[3 * j + 2] = x2; else if (j < 6) vpv[3 * j - 8] = x2;
  }
}

template <int ROT>
__device__ __forceinline__ void pack_qkv(const float* acc, uint32_t (&qlo)[10], uint32_t (&qhi)[10], uint32_t (&klo)[10],
                                         uint32_t (&khi)[10], uint32_t (&vlo)[10], uint32_t (&vhi)[10]) {
#pragma unroll
  for (int j = 0; j < 10; j++) {
    const int x = (j + ROT) % 10, tq = x < 8 ? x : 16 + x, tk = x < 8 ? 8 + x : 18 + x, tv = x < 8 ? 16 + x : 20 + x;
    khi[j] = pack2(acc[4 * tk + 2], acc[4 * tk + 3]);
    vhi[j] = movm(pack2(acc[4 * tv + 2], acc[4 * tv + 3]));
    qlo[j] = pack2(acc[4 * tq], acc[4 * tq + 1]);
    qhi[j] = pack2(acc[4 * tq + 2], acc[4 * tq + 3]);
    klo[j] = pack2(acc[4 * tk], acc[4 * tk + 1]);
    vlo[j] = pack2(acc[4 * tv], acc[4 * tv + 1]);
    asm volatile("" : "+r"(khi[j]), "+r"(qlo[j]), "+r"(qhi[j]), "+r"(klo[j]), "+r"(vlo[j]));
  }
}

template <int ROT> __device__ __forceinline__ void halo_send(const float* acc, uint4* ho, uint32_t tag) {
#pragma unroll
  for (int j = 0; j < 7; j++) {
    uint32_t x[3];
#pragma unroll
    for (int e = 0; e < 3; e++) {
      const int i = 3 * j + e, y = (i % 10 + ROT) % 10, tk = y < 8 ? 8 + y : 18 + y, tv = y < 8 ? 16 + y : 20 + y;
      x[e] = i < 10 ? pack2(acc[4 * tk + 2], acc[4 * tk + 3]) : i < 20 ? movm(pack2(acc[4 * tv + 2], acc[4 * tv + 3])) : 0u;
    }
    asm volatile("st.relaxed.gpu.global.v4.u32 [%0], {%1, %2, %3, %4};" ::"l"(ho + 32 * j), "r"(x[0]), "r"(x[1]), "r"(x[2]), "r"(tag) : "memory");
  }
}

__device__ __forceinline__ void attention(float* acc, uint32_t sb, int b, int par, int w, int lane, uint32_t tag) {
  const int g = lane >> 2, t = lane & 3;
  uint32_t klo[10], khi[10], vlo[10], vhi[10], qlo[10], qhi[10], kpv[10], vpv[10];
  if (w == 3 && b < NCTA - 8) {
    uint4* ho = g_halo + (b * 2 + par) * 224 + lane;
    if (tail_first(b & 7)) halo_send<8>(acc, ho, tag);
    else halo_send<0>(acc, ho, tag);
    TSIF(par == 0, 76);
    pin<120>(acc);
  }
  if (tail_first(b & 7)) pack_qkv<8>(acc, qlo, qhi, klo, khi, vlo, vhi);
  else pack_qkv<0>(acc, qlo, qhi, klo, khi, vlo, vhi);
  const uint32_t xa = sb + OFF_KVX + (par * 3) * 2560 + lane * 16;
  if (w < 3) {
    sts128(xa + w * 2560, khi[0], khi[1], khi[2], khi[3]);
    sts128(xa + w * 2560 + 512, khi[4], khi[5], khi[6], khi[7]);
    sts128(xa + w * 2560 + 1024, khi[8], khi[9], vhi[0], vhi[1]);
    sts128(xa + w * 2560 + 1536, vhi[2], vhi[3], vhi[4], vhi[5]);
    sts128(xa + w * 2560 + 2048, vhi[6], vhi[7], vhi[8], vhi[9]);
  }
  TSIF(par == 0 && w == 1, 64);
#pragma unroll
  for (int j = 0; j < 10; j++) vlo[j] = movm(vlo[j]);
  const bool far0 = 2 * t > g, far1 = 2 * t + 1 > g;
  const uint32_t mfar = (far0 ? 0x0000FFFFu : 0u) | (far1 ? 0xFFFF0000u : 0u);
  float slo[4][2], lg[2][2];
  uint32_t phi[4], plo[4], qml[4], qmh[4];
#pragma unroll
  for (int h = 0; h < 4; h++) {
    const int f = h == 0 ? 0 : h == 1 ? 3 : h == 2 ? 5 : 8, hf = h < 2 ? 2 : 7;
    const bool mine = (h & 1) ? t >= 2 : t < 2;
    qml[h] = mine ? qlo[hf] : 0u;
    qmh[h] = mine ? qhi[hf] : 0u;
    float a[4] = {0.f, 0.f, 0.f, 0.f}, c[4] = {0.f, 0.f, 0.f, 0.f};
    mma16816(a, qlo[f], qhi[f], qlo[f + 1], qhi[f + 1], klo[f], klo[f + 1]);
    mma16816(c, qlo[f], qhi[f], qlo[f + 1], qhi[f + 1], khi[f], khi[f + 1]);
    mma1688(a, qml[h], qmh[h], klo[hf]);
    mma1688(c, qml[h], qmh[h], khi[hf]);
    slo[h][0] = a[0];
    slo[h][1] = a[1];
    lg[h & 1][0] = far0 ? a[2] : c[2];
    lg[h & 1][1] = far1 ? a[3] : c[3];
    if (h & 1) softmax_two(lg, phi[h - 1], phi[h]);
  }
  TSIF(par == 0 && w == 1, 65);
  wg_sync(1 + par);
  TSIF(par == 0 && w == 1, 66);
  const bool nohist = (w == 0) && (b < 8);
  const uint4* hp = g_halo + ((b - 8) * 2 + par) * 224 + lane;
  uint32_t tg[7];
  if (w > 0) {
    const uint4 v0 = lds128(xa + (w - 1) * 2560), v1 = lds128(xa + (w - 1) * 2560 + 512), v2 = lds128(xa + (w - 1) * 2560 + 1024);
    const uint4 v3 = lds128(xa + (w - 1) * 2560 + 1536), v4 = lds128(xa + (w - 1) * 2560 + 2048);
    kpv[0] = v0.x; kpv[1] = v0.y; kpv[2] = v0.z; kpv[3] = v0.w; kpv[4] = v1.x; kpv[5] = v1.y; kpv[6] = v1.z; kpv[7] = v1.w;
    kpv[8] = v2.x; kpv[9] = v2.y; vpv[0] = v2.z; vpv[1] = v2.w; vpv[2] = v3.x; vpv[3] = v3.y; vpv[4] = v3.z; vpv[5] = v3.w;
    vpv[6] = v4.x; vpv[7] = v4.y; vpv[8] = v4.z; vpv[9] = v4.w;
  } else if (nohist) {
#pragma unroll
    for (int j = 0; j < 10; j++) kpv[j] = vpv[j] = 0u;
  } else {
    TSIF(par == 0, 77);
    halo_read(kpv, vpv, tg, hp);
  }
  if (w == 0 && !nohist) {
    int spins = 0;
    while (true) {
      bool ok = true;
#pragma unroll
      for (int j = 0; j < 7; j++) ok = ok && tg[j] == tag;
      if (__all_sync(0xffffffffu, ok) || ++spins > SPIN_LIMIT) break;
      halo_read(kpv, vpv, tg, hp);
    }
    TSIF(par == 0, 79);
  }
#pragma unroll
  for (int h = 0; h < 4; h++) {
    const int f = h == 0 ? 0 : h == 1 ? 3 : h == 2 ? 5 : 8, hf = h < 2 ? 2 : 7;
    float a[4] = {0.f, 0.f, 0.f, 0.f};
    mma16816(a, qlo[f], qhi[f], qlo[f + 1], qhi[f + 1], kpv[f], kpv[f + 1]);
    mma1688(a, qml[h], qmh[h], kpv[hf]);
    const float ninf = __int_as_float(0xff800000);
    lg[h & 1][0] = far0 ? (nohist ? ninf : a[0]) : slo[h][0];
    lg[h & 1][1] = far1 ? (nohist ? ninf : a[1]) : slo[h][1];
    if (h & 1) softmax_two(lg, plo[h - 1], plo[h]);
  }
  TSIF(par == 0 && w <= 1, 67 + w);
  uint32_t ov[20];
#pragma unroll
  for (int hp = 0; hp < 2; hp++) {
    const int hf = hp ? 7 : 2;
    float sh[4] = {0.f, 0.f, 0.f, 0.f}, i0 = 0.f, i1 = 0.f;
#pragma unroll
    for (int e = 0; e < 2; e++) {
      const int h = 2 * hp + e, f = h == 0 ? 0 : h == 1 ? 3 : h == 2 ? 5 : 8;
      const uint32_t a0 = plo[h] & mfar, a2 = plo[h] & ~mfar, a3 = phi[h] & mfar, c1 = phi[h] & ~mfar;
      float sum[4] = {0.f, 0.f, 0.f, 0.f};
      mma1688(sum, plo[h], phi[h], 0x3F803F80u);
      const float r0 = rcp(sum[0]), r1 = rcp(sum[2]);
#pragma unroll
      for (int j = f; j < f + 2; j++) {
        float o[4] = {0.f, 0.f, 0.f, 0.f};
        mma16816(o, a0, 0u, a2, a3, vpv[j], vlo[j]);
        mma1688(o, 0u, c1, vhi[j]);
        ov[2 * j] = pack2(o[0] * r0, o[1] * r0);
        ov[2 * j + 1] = pack2(o[2] * r1, o[3] * r1);
      }
      const bool mine = e ? g >= 4 : g < 4;
      mma16816(sh, a0, 0u, a2, a3, mine ? vpv[hf] : 0u, mine ? vlo[hf] : 0u);
      mma1688(sh, 0u, c1, mine ? vhi[hf] : 0u);
      if (e == 0 || t >= 2) {
        i0 = r0;
        i1 = r1;
      }
    }
    ov[2 * hf] = pack2(sh[0] * i0, sh[1] * i0);
    ov[2 * hf + 1] = pack2(sh[2] * i1, sh[3] * i1);
  }
  TS(32 + 4 * par + w);
  mbar_wait(sb + OFF_BAR + 8 * B_P1, 0);
  const uint32_t oa = sb + OFF_OA + (lane >> 4) * 2048 + (32 * w + 2 * (lane & 15) + par) * 16;
#pragma unroll
  for (int j = 0; j < 5; j++) stsm4(oa + 4096 * j, ov + 4 * j);
  TSIF(par == 0 && w == 0, 120);
  fence_async_smem();
  TSIF(par == 0 && w == 0, 121);
  __syncwarp();
  if (lane == 0) mbar_arrive(sb + OFF_BAR + 8 * B_ATTN);
  TSM(w == 0 || w == 2, 122 + par + (w == 2 ? 3 : 0));
}

struct Maps {
  CUtensorMap x, wm, wt, k, v, y, wo, qm, qt, om, ot, yl, ol;
};

__device__ __forceinline__ void load_stage(uint32_t sb, int kb, int b, const Maps& m) {
  const uint32_t st = sb + (kb & 3) * STAGE_BYTES, bar = sb + OFF_BAR + 8 * (B_FULL1 + (kb & 3));
  const int r = b >> 3, hg = b & 7, slab = kb - KV_KB;
  const bool kv = slab >= 0 && slab < 5;
  const uint32_t kbar = sb + OFF_BAR + 8 * (B_KV + slab), dst = sb + OFF_KVS + slab * KVS_BYTES;
  mbar_expect_tx(bar, STAGE_BYTES);
  if (kv) mbar_expect_tx(kbar, KVS_BYTES);
  tma_3d(st, &m.x, 64 * kb, 64 * r, 0, bar);
  tma_3d(st + ST_W, &m.wm, 80 * hg + (tail_first(hg) ? 16 : 0), 64 * kb, 0, bar);
  tma_3d(st + ST_WT, &m.wt, 80 * hg + (tail_first(hg) ? 0 : 64), 64 * kb, 0, bar);
  if (kv) tma_3d(dst, &m.k, 0, 32 * (b >> 1) - 3, 2 * slab + (b & 1), kbar);
  if (kv) tma_3d(dst + KVS_V, &m.v, 0, 32 * (b >> 1), 2 * slab + (b & 1), kbar);
}

__global__ void __launch_bounds__(NTHR, 1) fused_kernel(const __grid_constant__ Maps m, const Params p) {
  extern __shared__ __align__(1024) uint8_t smem[];
  const uint32_t sb = (uint32_t)__cvta_generic_to_shared(smem);
  const uint32_t bars = sb + OFF_BAR;
  const int tid = threadIdx.x, lane = tid & 31;
  int b = blockIdx.x;
  b = (((b & 63) >> 3) * 2 + (b & 1)) * 8 + (((b < 64 ? 0x6521 : 0x7430) >> (4 * ((b >> 1) & 3))) & 7);
  const int r = b >> 3, hg = b & 7;

  if (tid == T_ISSUE) {
    TSM(true, 0);
    mbar_init(bars + 8 * B_F0, 1);
    fence_async_smem();
    mbar_expect_tx(bars + 8 * B_F0, ST_WT);
    tma_3d(sb, &m.x, 0, 64 * r, 0, bars + 8 * B_F0);
    tma_3d(sb + ST_W, &m.wm, 80 * hg + (tail_first(hg) ? 16 : 0), 0, 0, bars + 8 * B_F0);
#pragma unroll
    for (int i = 0; i < 4; i++) mbar_init(bars + 8 * (B_FULL1 + i), 1);
    fence_async_smem();
    mbar_expect_tx(bars + 8 * B_FULL1, STAGE_BYTES - ST_WT);
    tma_3d(sb + ST_WT, &m.wt, 80 * hg + (tail_first(hg) ? 0 : 64), 0, 0, bars + 8 * B_FULL1);
    load_stage(sb, 1, b, m);
  } else if (tid == T_INIT) {
#pragma unroll
    for (int i = 0; i < B_F0; i++) mbar_init(bars + 8 * i, i < B_GATE ? 8 : i < B_CVD ? 4 : i == B_CVD ? 20 : 1);
    fence_async_smem();
  }
  const int warp = __shfl_sync(0xffffffffu, tid >> 5, 0), wg = warp >> 2, w = warp & 3;
  __syncthreads();

  if (wg == 3) {
    asm volatile("setmaxnreg.dec.sync.aligned.u32 56;");
    if (w == 0) {
      if (lane == 0) {
#pragma unroll 1
        for (int kb = 2; kb < 10; kb++) {
          if (kb >= 4) mbar_wait(bars + 8 * (kb == 7 ? B_E3 : B_EMPTY1 + (kb & 3)), (kb >> 3) & 1);
          TSIF(kb >= 4, 44 + kb);
          load_stage(sb, kb, b, m);
          TSIF(kb == 3, 60);
          if (kb == 9) mbar_arrive(bars + 8 * B_LAST);
        }
        mbar_wait(bars + 8 * B_WOP, 0);
        mbar_wait(bars + 8 * B_EPOCH, 0);
        flag_wait(g_cnt + C_W + 32 * hg, (lds32(sb + OFF_EPOCH) + 1) * 16);
        TS(30);
#pragma unroll 1
        for (int j = 0; j < 8; j++) {
          if (j >= 6) mbar_wait(bars + 8 * (B_EMPTY2 + j - 6), 0);
          if (j == 4) mbar_wait(bars + 8 * B_ORB, 0);
          TSIF(j >= 6, 100 + j);
          mbar_expect_tx(bars + 8 * (B_FULL2 + j), j == 0 ? WO_BYTES : j == 5 ? O_BYTES + WO_BYTES + 512 : O_BYTES + WO_BYTES);
          bulk_load(sb + off_w(j), g_WO + (hg * 8 + step_src(hg, j)) * 800, WO_BYTES, bars + 8 * (B_FULL2 + j));
        }
        mbar_wait(bars + 8 * (B_EMPTY2 + 3), 0);
        mbar_expect_tx(bars + 8 * B_QF, O_BYTES);
        tma_2d(sb + OFF_QS, &m.qm, 80 * hg, 128 * r, bars + 8 * B_QF);
        tma_2d(sb + OFF_QT, &m.qt, 80 * hg + 64, 128 * r, bars + 8 * B_QF);
      }
    } else if (w == 1) {
      unsigned epoch = 0;
      if (lane == 0) {
        epoch = atomicAdd(g_cnt + C_LAUNCH, 1u) / NCTA;
        asm volatile("st.shared.u32 [%0], %1;" ::"r"(sb + OFF_EPOCH), "r"(epoch) : "memory");
        mbar_arrive(bars + 8 * B_EPOCH);
        mbar_wait(bars + 8 * B_KVD, 0);
        mbar_expect_tx(bars + 8 * B_HB, 5 * 4096);
#pragma unroll 1
        for (int c = 0; c < 5; c++) {
          if (c == 3) mbar_wait(bars + 8 * B_S3, 0);
          bulk_load(sb + off_ch(c) + U_BYTES, p.ssm_k + (5 * b + c) * SEQ, 4096, bars + 8 * B_HB);
        }
#pragma unroll
        for (int c = 0; c < 4; c++) mbar_expect_tx(bars + 8 * (B_U + c), c < 3 ? U_BYTES : 2 * U_BYTES);
        const uint4* usrc = g_U + 5 * b * U_PITCH;
        mbar_wait(bars + 8 * B_USIG, 0);
        flag_wait(g_cnt + C_PREP + 32 * (b & 15), (epoch + 1) * NCTA);
        TS(23);
#pragma unroll
        for (int c = 0; c < 5; c++) {
          if (c == 3) mbar_wait(bars + 8 * (B_U + 2), 0);
          bulk_load(sb + off_ch(c), usrc + c * U_PITCH, U_BYTES, bars + 8 * (B_U + (c < 3 ? c : 3)));
          TSIF(c == 0 || c == 4, 116 + (c >> 2));
        }
      }
      epoch = __shfl_sync(0xffffffffu, epoch, 0);
      if (lane < 8) {
        const int src = (b & ~7) | step_src(hg, lane);
        mbar_wait(bars + 8 * B_ATTN, 0);
        TS(20);
        bool seen = false;
#pragma unroll 1
        for (int spins = 0; spins < SPIN_LIMIT; spins++) {
          const bool now = !seen && (int)(flag_read(g_cnt + C_O + 32 * src) - (epoch + 1)) >= 0;
          if (now && lane >= 1 && lane < 4) bulk_load(sb + off_o(lane), g_O + src * 1280, O_BYTES, bars + 8 * (B_FULL2 + lane));
          seen = seen || now;
          if (__all_sync(0xff, seen)) break;
        }
        TS(21);
        if (lane == 5) bulk_load(sb + OFF_GATE, g_gate + 128 * r, 512, bars + 8 * (B_FULL2 + 5));
#pragma unroll 1
        for (int j = 4; j < 8; j++) {
          if (lane == j) {
            mbar_wait(bars + 8 * (j < 6 ? B_C34 : B_EMPTY2 + j - 6), 0);
            bulk_load(sb + off_o(j), g_O + src * 1280, O_BYTES, bars + 8 * (B_FULL2 + j));
          }
          __syncwarp(0xff);
        }
        TS(22);
      }
    } else if (w == 2) {
      mbar_wait(bars + 8 * B_PREP, 0);
      flag_signal(g_cnt + C_PREP, 16, lane);
      TS(25);
      if (lane == 0) {
        mbar_arrive(bars + 8 * B_USIG);
        mbar_expect_tx(bars + 8 * B_ORB, O_BYTES / 4 + 64);
        mbar_wait(bars + 8 * B_GATE, 0);
        publish(g_gate + 16 * b, sb + OFF_GATE + 64 * hg, 64);
        bulk_load(sb + OFF_GATE + 64 * hg, g_gate + 16 * b, 64, bars + 8 * B_ORB);
        mbar_wait(bars + 8 * B_ATTN, 0);
        publish(g_O + b * 1280, sb + OFF_OA, O_BYTES);
        tma_2d(sb + OFF_KVX + 10240, &m.ol, 48, b * 160, bars + 8 * B_ORB);
        TS(74);
        mbar_wait(bars + 8 * B_ORB, 0);
        flag_bump(g_cnt + C_O + 32 * b);
        TS(26);
      }
    } else {
      if (lane == 0) {
        uint4* dst = g_WO + (hg * 8 + (r >> 1)) * 800 + (r & 1) * 80;
        mbar_wait(bars + 8 * B_S3, 0);
        asm volatile("cp.async.bulk.prefetch.L2.global [%0], 6400;" ::"l"(p.wo + b * 3200) : "memory");
        mbar_wait(bars + 8 * B_P1, 0);
        mbar_wait(bars + 8 * WB_TRIG, 0);
        mbar_expect_tx(bars + 8 * B_WST, WO_BYTES / 2);
        tma_3d(sb + OFF_WA, &m.wo, 0, 40 * r, 5 * hg, bars + 8 * B_WST);
        mbar_wait(bars + 8 * B_WST, 0);
#pragma unroll 1
        for (int n = 0; n < 5; n++) bulk_store(dst + 160 * n, sb + OFF_WA + 1280 * n, 1280);
        bulk_wait_read();
        mbar_expect_tx(bars + 8 * B_WST, WO_BYTES / 2);
#pragma unroll 1
        for (int n = 0; n < 5; n++) bulk_load(sb + OFF_WA + 1280 * n, dst + 160 * n, 1280, bars + 8 * B_WST);
        mbar_wait(bars + 8 * B_WST, 1);
        flag_bump(g_cnt + C_W + 32 * hg);
        mbar_arrive(bars + 8 * B_WOP);
        TS(71);
        mbar_expect_tx(bars + 8 * B_C34, 3 * (U_BYTES / 4));
        mbar_expect_tx(bars + 8 * B_YRB, 2 * (U_BYTES / 4));
#pragma unroll 1
        for (int c = 0; c < 5; c++) {
          mbar_wait(bars + 8 * (B_YST + c), 0);
          publish(g_U + (5 * b + c) * U_PITCH, sb + off_ch(c), U_BYTES);
          tma_2d(sb + off_ch(c), &m.yl, 48, (5 * b + c) * (U_PITCH / 8), bars + 8 * (c < 3 ? B_C34 : B_YRB));
        }
        TS(75);
        mbar_wait(bars + 8 * B_C34, 0);
        mbar_wait(bars + 8 * B_YRB, 0);
        flag_bump(g_cnt + C_Y + 32 * (b >> 4));
        TS(27);
        mbar_expect_tx(bars + 8 * B_YFULL, 20480);
        flag_wait(g_cnt + C_Y + 32 * hg, (lds32(sb + OFF_EPOCH) + 1) * 16);
        TS(24);
        tma_2d(sb + OFF_YT, &m.y, 128 * r, 80 * hg, bars + 8 * B_YFULL);
        tma_2d(sb + OFF_YT + 10240, &m.y, 128 * r + 64, 80 * hg, bars + 8 * B_YFULL);
      }
    }
  } else {
    asm volatile("setmaxnreg.inc.sync.aligned.u32 152;");
    if (wg < 2) {
      float acc[120];
#pragma unroll
      for (int i = 0; i < 120; i++) acc[i] = 0.f;
      const uint32_t da = desc_lo(sb + wg * 8192, 16), db = desc_lo(sb + ST_W, 8192), dc = desc_lo(sb + ST_WT, 2048);
      mbar_wait(bars + 8 * B_F0, 0);
      TSIF(w == 0 && wg == 0, 1);
      wg_fence();
#pragma unroll
      for (int k = 0; k < 4; k++) WgSST<192>::mma<HI_SW128, HI_SW128>(acc, da + 2 * k, db + 128 * k, 1);
      wg_commit();
      mbar_wait(bars + 8 * B_FULL1, 0);
      wg_fence();
#pragma unroll
      for (int k = 0; k < 4; k++) WgSST<48>::mma<HI_SW128, HI_SW32>(acc + 96, da + 2 * k, dc + 32 * k, 1);
      wg_commit();
#pragma unroll 1
      for (int kb = 1; kb < 10; kb++) {
        mbar_wait(bars + 8 * (B_FULL1 + (kb & 3)), (kb >> 2) & 1);
        const uint32_t so = (kb & 3) * (STAGE_BYTES >> 4);
        wg_fence();
#pragma unroll
        for (int k = 0; k < 4; k++) {
          WgSST<192>::mma<HI_SW128, HI_SW128>(acc, da + so + 2 * k, db + so + 128 * k, 1);
          WgSST<48>::mma<HI_SW128, HI_SW32>(acc + 96, da + so + 2 * k, dc + so + 32 * k, 1);
        }
        wg_commit();
        wg_wait<1>();
        if (lane == 0) mbar_arrive(bars + 8 * (kb == 4 ? B_E3 : B_EMPTY1 + ((kb - 1) & 3)));
      }
      mbar_wait(bars + 8 * B_EPOCH, 0);
      const uint32_t tag = lds32(sb + OFF_EPOCH) + 1;
      mbar_wait(bars + 8 * B_S3, 0);
      wg_wait<0>();
      pin<120>(acc);
      if (lane == 0) mbar_arrive(bars + 8 * B_P1);
      TSM(w == 0, 3 + wg);
      attention(acc, sb, b, wg, w, lane, tag);
    } else {
      const int tw = tid & 127, chl = 64 * (b & 1) + 8 * w + (lane >> 2);
      uint4* up = g_U + chl * U_PITCH + ((4 * (b >> 1) + (lane & 3)) ^ ((b >> 2) & 1));
      uint2 sw[10];
      uint32_t dv = 0;
      if (lane < 5) dv = __ldg(reinterpret_cast<const unsigned short*>(p.ssm_D) + 5 * b + lane);
#pragma unroll
      for (int i = 0; i < 10; i++) sw[i] = ldg64(reinterpret_cast<const uint2*>(p.shift_k) + chl + 128 * (i >> 1) + 32 * (i & 1));
      uint32_t tab[12];
      uint32_t tt[2];
      fft_tables(tab, tw);
      fft_twiddles(tt, tw);
      uint4 res[10];
#pragma unroll
      for (int i = 0; i < 10; i++) res[i] = make_uint4(0, 0, 0, 0);
#pragma unroll 1
      for (int slab = 0; slab < 5; slab++) {
#pragma unroll
        for (int i = 0; i < 8; i++) res[i] = res[i + 2];
        prep_slab(res + 8, sw, sb, slab, w, lane);
        TSIF(w == 0, 99 + 4 * slab);
#pragma unroll
        for (int i = 0; i < 8; i++) sw[i] = sw[i + 2];
      }
      TSIF(w == 0, 28);
      __syncwarp();
      if (lane == 0) mbar_arrive(bars + 8 * B_KVD + ((res[8].x ^ res[9].x) & p.zero));
      mbar_wait(bars + 8 * B_KVD, 0);
      fft_tables_store(tab, sb, tw);
      mbar_wait(bars + 8 * B_LAST, 0);
#pragma unroll
      for (int i = 0; i < 10; i++) up[(128 * (i >> 1) + 32 * (i & 1)) * U_PITCH] = res[i];
      __syncwarp();
      if (lane == 0) mbar_arrive(bars + 8 * B_PREP);
      TSIF(w == 0, 5);
      mbar_wait(bars + 8 * B_LAST, 0);
      prep_gate(p, sb, b, w, lane);
      __syncwarp();
      if (lane == 0) mbar_arrive(bars + 8 * B_GATE);
      TSIF(w == 0, 72);
      mbar_wait(bars + 8 * B_HB, 0);
      TSIF(w == 0, 2);
      const uint32_t ha = sb + U_BYTES + ((tw >> 3) * 16 + 8 + (tw & 7)) * 16;
      uint4 hv[5];
#pragma unroll
      for (int c = 0; c < 5; c++) hv[c] = lds128(ha + off_ch(c));
      __syncwarp();
#pragma unroll
      for (int c = 0; c < 5; c++) sts128((ha ^ 16) + off_ch(c), hv[c].x, hv[c].y, hv[c].z, hv[c].w);
      asm volatile("st.shared.v2.u32 [%0], {%1, %2};" ::"r"(sb + OFF_TT + 8 * tw), "r"(tt[0]), "r"(tt[1]) : "memory");
      if (tw < 5) asm volatile("st.shared.f32 [%0], %1;" ::"r"(sb + OFF_D + 4 * tw), "f"(bf_lo(dv) * 0.125f) : "memory");
      fence_async_smem();
      __syncwarp();
      if (lane == 0) mbar_arrive(bars + 8 * B_HA);
      TSIF(w == 0, 6);
    }

    FftConst fc;
    TSM(w == 0 && wg == 0, 104);
    mbar_wait(bars + 8 * B_HA, 0);
    fft_matrices(fc, sb, w, lane);
    TSM(w == 0 && wg == 0, 105);
    TSM(w == 0 && wg == 2, 124);
#pragma unroll 1
    for (uint32_t tasks = wg == 0 ? TASK0 : wg == 1 ? TASK1 : TASK2; tasks; tasks >>= 4) {
      const int c = (tasks & 7) - 1;
      conv_channel(fc, sb, c, wg, w, lane);
      if (lane == 0) mbar_arrive(bars + 8 * (B_YST + c));
      TSM(w == 0, 10 + c);
    }

    if (wg != 1) {
      const int wg = warp >> 3;
      const int g = lane >> 2;
      float acc[40];
#pragma unroll
      for (int i = 0; i < 40; i++) acc[i] = 0.f;
      const uint32_t da = desc_lo(sb + wg * 1024, 2048), db = desc_lo(sb, 2560);
      mbar_wait(bars + 8 * B_ORB, 0);
      mbar_wait(bars + 8 * B_FULL2, 0);
      TSM(w == 0, 15 + wg);
#pragma unroll 1
      for (int j = 0; j < 8; j++) {
        if (E_WAIT && j == 0) mbar_wait(bars + 8 * (B_YST + 3), 0);
        if (j == (wg ? WO_E1 : WO_E0)) mbar_wait(bars + 8 * B_CVD, 0);
        mbar_wait(bars + 8 * (B_FULL2 + j), 0);
        TSM(w == 0 && wg == 0, 44 + (j < 4 ? j : j + 6));
        const uint32_t oa = da + (off_o(j) >> 4), ob = db + (off_w(j) >> 4);
        wg_fence();
#pragma unroll
        for (int k = 0; k < 5; k++) WgSST<80>::mma<HI_NONE, HI_SW32>(acc, oa + 256 * k, ob + 32 * k, 1);
        wg_commit();
        wg_wait<1>();
        if (j >= 1 && j <= 4 && lane == 0) mbar_arrive(bars + 8 * (B_EMPTY2 + j - 1));
      }
      TSIF(w == 0 && wg == 0, 113);
      const int tr = 64 * wg + 16 * w + (lane & 15);
      const uint32_t fm = sb + OFF_QS + tr * 128, fx = (lane >> 4) ^ (tr & 7);
      const uint32_t ft = sb + OFF_QT + tr * 32 + (((lane >> 4) ^ (tr >> 2)) & 1) * 16;
      const float g0 = __uint_as_float(lds32(sb + OFF_GATE + (64 * wg + 16 * w + g) * 4));
      const float g1 = __uint_as_float(lds32(sb + OFF_GATE + (64 * wg + 16 * w + 8 + g) * 4));
      const uint32_t ga = pack2(g0, g0), gb = pack2(g1, g1);
      const uint32_t na = pack2(1.f - g0, 1.f - g0), nb = pack2(1.f - g1, 1.f - g1);

      uint32_t qf[20];
      mbar_wait(bars + 8 * B_QF, 0);
      TSM(w == 0 && wg == 0, 99);
#pragma unroll
      for (int j = 0; j < 5; j++) ldsm4(qf + 4 * j, j < 4 ? fm + ((fx ^ (2 * j)) << 4) : ft);
#pragma unroll
      for (int i = 0; i < 20; i++) {
        qf[i] = bmul((i & 1) ? gb : ga, qf[i]);
        asm volatile("" : "+r"(qf[i]));
      }

      wg_wait<0>();
      pin<40>(acc);
      TSM(w == 0, 17 + wg);
      uint32_t pb[20];
#pragma unroll
      for (int j = 0; j < 10; j++) {
        pb[2 * j] = bmul(na, pack2(acc[4 * j], acc[4 * j + 1]));
        pb[2 * j + 1] = bmul(nb, pack2(acc[4 * j + 2], acc[4 * j + 3]));
        asm volatile("" : "+r"(pb[2 * j]), "+r"(pb[2 * j + 1]));
      }
      const uint32_t ya = sb + OFF_YT + wg * 10240 + ((lane >> 4) * 8 + (lane & 7)) * 128 +
                          (((2 * w + (((lane >> 3) & 1) ^ wg)) ^ (lane & 7)) << 4);
      mbar_wait(bars + 8 * B_YFULL, 0);
      TSM(w == 0 && wg == 0, 19);
#pragma unroll
      for (int j = 0; j < 5; j++) {
        uint32_t y[4];
        ldsm4t(y, ya + 2048 * j);
#pragma unroll
        for (int i = 0; i < 4; i++)
          qf[4 * j + i] = bfma(qf[4 * j + i], y[i], pb[4 * j + i]);
      }
#pragma unroll
      for (int j = 0; j < 5; j++) stsm4(j < 4 ? fm + ((fx ^ (2 * j)) << 4) : ft, qf + 4 * j);
      fence_async_smem();
      __syncwarp();
      if (lane == 0) {
        const int row = 64 * wg + 16 * w;
        asm volatile("cp.async.bulk.tensor.2d.global.shared::cta.bulk_group [%0, {%2, %3}], [%1];"
                     ::"l"(&m.om), "r"(sb + OFF_QS + row * 128), "r"(80 * hg), "r"(128 * r + row) : "memory");
        asm volatile("cp.async.bulk.tensor.2d.global.shared::cta.bulk_group [%0, {%2, %3}], [%1];"
                     ::"l"(&m.ot), "r"(sb + OFF_QT + row * 32), "r"(80 * hg + 64), "r"(128 * r + row) : "memory");
        asm volatile("cp.async.bulk.commit_group;\ncp.async.bulk.wait_group.read 0;" ::: "memory");
      }
      TSM(w == 0 || w == 3, 40 + 2 * wg + (w & 1));
    }
  }
}

typedef CUresult (*EncodeFn)(CUtensorMap*, CUtensorMapDataType, cuuint32_t, void*, const cuuint64_t*, const cuuint64_t*,
                             const cuuint32_t*, const cuuint32_t*, CUtensorMapInterleave, CUtensorMapSwizzle,
                             CUtensorMapL2promotion, CUtensorMapFloatOOBfill);

void encode(EncodeFn fn, CUtensorMap* tm, const void* base, int rank, const cuuint64_t* dims, const cuuint64_t* strides,
            const cuuint32_t* box, CUtensorMapSwizzle swz) {
  const cuuint32_t ones[3] = {1, 1, 1};
  fn(tm, CU_TENSOR_MAP_DATA_TYPE_BFLOAT16, rank, const_cast<void*>(base), dims, strides, box, ones,
     CU_TENSOR_MAP_INTERLEAVE_NONE, swz, CU_TENSOR_MAP_L2_PROMOTION_L2_128B, CU_TENSOR_MAP_FLOAT_OOB_FILL_NONE);
}

}

extern "C" void kernel_launch(void* const* d_in, const int* in_sizes, int n_in, void* d_out, int out_size) {
  (void)in_sizes; (void)n_in; (void)out_size;
  Params p;
  p.q = (const __nv_bfloat16*)d_in[0];
  p.k = (const __nv_bfloat16*)d_in[1];
  p.v = (const __nv_bfloat16*)d_in[2];
  p.shift_k = (const __nv_bfloat16*)d_in[3];
  p.ssm_k = (const __nv_bfloat16*)d_in[4];
  p.ssm_D = (const __nv_bfloat16*)d_in[5];
  p.wqkv = (const __nv_bfloat16*)d_in[7];
  p.wo = (const __nv_bfloat16*)d_in[8];
  p.gate_w = (const __nv_bfloat16*)d_in[9];
  p.out = (__nv_bfloat16*)d_out;
  p.zero = 0;

  static EncodeFn fn = nullptr;
  static void *yaddr = nullptr, *oaddr = nullptr;
  if (!fn) {
    cudaDriverEntryPointQueryResult qr;
    void* f = nullptr;
    cudaGetDriverEntryPoint("cuTensorMapEncodeTiled", &f, cudaEnableDefault, &qr);
    fn = (EncodeFn)f;
    cudaGetSymbolAddress(&yaddr, g_U);
    cudaGetSymbolAddress(&oaddr, g_O);
    cudaFuncSetAttribute(fused_kernel, cudaFuncAttributeMaxDynamicSharedMemorySize, SMEM_BYTES);
  }
  Maps m;
  {
    const cuuint64_t dims[3] = {640, 1024, 2}, st[2] = {2560, 1280};
    const cuuint32_t box[3] = {64, 64, 2};
    encode(fn, &m.x, p.q, 3, dims, st, box, CU_TENSOR_MAP_SWIZZLE_128B);
  }
  {
    const cuuint64_t dims[3] = {640, 640, 3}, st[2] = {3840, 1280};
    const cuuint32_t box[3] = {64, 64, 3}, boxt[3] = {16, 64, 3};
    encode(fn, &m.wm, p.wqkv, 3, dims, st, box, CU_TENSOR_MAP_SWIZZLE_128B);
    encode(fn, &m.wt, p.wqkv, 3, dims, st, boxt, CU_TENSOR_MAP_SWIZZLE_32B);
  }
  {
    const cuuint64_t dims[3] = {64, 2048, 10}, st[2] = {1280, 128};
    const cuuint32_t boxk[3] = {64, 35, 1}, boxv[3] = {64, 32, 1};
    encode(fn, &m.k, p.k, 3, dims, st, boxk, CU_TENSOR_MAP_SWIZZLE_128B);
    encode(fn, &m.v, p.v, 3, dims, st, boxv, CU_TENSOR_MAP_SWIZZLE_128B);
  }
  {
    const cuuint64_t dims[3] = {16, 640, 40}, st[2] = {1280, 32};
    const cuuint32_t box[3] = {16, 40, 5};
    encode(fn, &m.wo, p.wo, 3, dims, st, box, CU_TENSOR_MAP_SWIZZLE_32B);
  }
  {
    const cuuint64_t dims[2] = {2048, 640}, st[1] = {U_PITCH * 16};
    const cuuint32_t box[2] = {64, 80};
    encode(fn, &m.y, yaddr, 2, dims, st, box, CU_TENSOR_MAP_SWIZZLE_128B);
    const cuuint64_t dl[2] = {64, DIM * U_PITCH / 8}, dol[2] = {64, NCTA * 160}, sl[1] = {128};
    const cuuint32_t bl[2] = {16, 32}, bol[2] = {16, 160};
    encode(fn, &m.yl, yaddr, 2, dl, sl, bl, CU_TENSOR_MAP_SWIZZLE_NONE);
    encode(fn, &m.ol, oaddr, 2, dol, sl, bol, CU_TENSOR_MAP_SWIZZLE_NONE);
  }
  {
    const cuuint64_t dims[2] = {640, 2048}, st[1] = {1280};
    const cuuint32_t bqm[2] = {64, 128}, bqt[2] = {16, 128}, bom[2] = {64, 16}, bot[2] = {16, 16};
    encode(fn, &m.qm, p.q, 2, dims, st, bqm, CU_TENSOR_MAP_SWIZZLE_128B);
    encode(fn, &m.qt, p.q, 2, dims, st, bqt, CU_TENSOR_MAP_SWIZZLE_32B);
    encode(fn, &m.om, p.out, 2, dims, st, bom, CU_TENSOR_MAP_SWIZZLE_128B);
    encode(fn, &m.ot, p.out, 2, dims, st, bot, CU_TENSOR_MAP_SWIZZLE_32B);
  }
  fused_kernel<<<NCTA, NTHR, SMEM_BYTES>>>(m, p);
}
```

```cpp
#include <cuda.h>
#include <cuda_bf16.h>
#include <cuda_runtime.h>
#include <stdint.h>

namespace {

constexpr int SEQ = 2048, DIM = 640, NCTA = 128, NTHR = 512;

#define KV_KB 2
#define DEV_EXIT 0
#define FENCE_LO 0
#define FENCE_HI 0
#define WB_TRIG B_USIG
#define T_ISSUE 288
#define NS0 2
#define W_FIRST 0
#define T_INIT 448
#define TASK0 0x3
#define TASK1 0x52
#define TASK2 0x41

constexpr uint32_t STAGE_BYTES = 47104, ST_W = 16384, ST_WT = 40960;
constexpr uint32_t O_BYTES = 20480, WO_BYTES = 12800;
constexpr uint32_t OFF_OA = 0;
constexpr uint32_t OFF_QS = 3 * O_BYTES, OFF_QT = OFF_QS + 16384;
constexpr uint32_t OFF_WC = 81920;
constexpr uint32_t OFF_WA = 94720;
constexpr uint32_t OFF_GATE = 145920;
constexpr uint32_t OFF_TT = 146432;
constexpr uint32_t OFF_KVX = 148480;
constexpr uint32_t OFF_CH3 = 163840;
constexpr uint32_t CH_BYTES = 12288, U_BYTES = 4096;
constexpr uint32_t OFF_FT = 225280, OFF_GT = 229376;
constexpr uint32_t OFF_CH0 = 188416;
constexpr uint32_t OFF_KVS = OFF_CH0, KVS_V = 4480, KVS_BYTES = 8576;
constexpr uint32_t OFF_YT = 163840;
constexpr uint32_t OFF_BAR = 231936;
constexpr uint32_t SMEM_BYTES = OFF_BAR + 512;

enum : uint32_t {
  B_EMPTY1 = 0, B_S3 = 3, B_E3 = 4, B_EMPTY2 = 5, B_ATTN = 9, B_P1 = 10,
  B_GATE = 11, B_HA = 12, B_KVD = 13, B_PREP = 14, B_YST = 15,
  B_CVD = 20,
  B_FULL2 = 21, B_U = 29, B_KV = 33, B_HB = 38, B_C34 = 39, B_YRB = 40, B_YFULL = 41, B_EPOCH = 42, B_LAST = 43,
  B_WOP = 44, B_USIG = 45, B_WST = 46, B_QF = 47, B_ORB = 48,
  B_F0 = 49, B_FULL1 = 50
};
constexpr uint32_t OFF_EPOCH = OFF_BAR + 8 * 58, OFF_D = OFF_BAR + 8 * 60;
__device__ __forceinline__ uint32_t off_o(int j) { return j < 4 ? OFF_OA + j * O_BYTES : j < 6 ? OFF_CH0 + (j - 4) * O_BYTES : OFF_OA + (j - 6) * O_BYTES; }
__device__ __forceinline__ uint32_t off_w(int j) { return j < 4 ? OFF_WA + j * WO_BYTES : j == 4 ? OFF_KVX : j == 5 ? OFF_WC : OFF_WA + (j - 6) * WO_BYTES; }
__device__ __forceinline__ int step_src(int hg, int j) { return j == 0 ? hg : j <= hg ? j - 1 : j; }
__device__ __forceinline__ bool tail_first(int hg) { return (hg & 3) == 3; }
__device__ __forceinline__ uint32_t off_ch(int c) { return (c < 3 ? OFF_CH0 : OFF_CH3 - 3 * CH_BYTES) + c * CH_BYTES; }

#define U_PITCH 264
__device__ __align__(1024) uint4 g_U[DIM * U_PITCH];
__device__ __align__(128) uint4 g_O[NCTA * 1280];
__device__ uint4 g_WO[64 * 800];
__device__ uint4 g_halo[NCTA * 2 * 7 * 32];
__device__ __align__(128) float g_gate[SEQ];
__device__ unsigned g_cnt[32 * (1 + 2 * 16 + 8 + NCTA)];
constexpr int C_LAUNCH = 0, C_PREP = 32, C_Y = 32 * 17, C_W = 32 * 33, C_O = 32 * 41;

#define TSM(cond, slot) do { } while (0)
#define TSIF(cond, slot) do { if (__LINE__ >= FENCE_LO && __LINE__ < FENCE_HI) sched_fence(); } while (0)
__device__ __forceinline__ void sched_fence() {
  asm volatile("{\n.reg .pred p;\n.reg .u32 c;\nmov.u32 c, %%clock;\nsetp.eq.u32 p, c, 0;\n@p st.shared.u32 [%0], c;\n}"
               ::"r"(1024 + OFF_EPOCH + 4) : "memory");
}
#define TS(slot) TSIF(true, slot)

struct Params {
  const __nv_bfloat16 *q, *k, *v, *shift_k, *ssm_k, *ssm_D, *wqkv, *wo, *gate_w;
  __nv_bfloat16* out;
  uint32_t zero;
};

constexpr int SPIN_LIMIT = 1 << 17;

__device__ __forceinline__ void mbar_init(uint32_t bar, uint32_t count) {
  asm volatile("mbarrier.init.shared::cta.b64 [%0], %1;" ::"r"(bar), "r"(count) : "memory");
}
__device__ __forceinline__ void mbar_expect_tx(uint32_t bar, uint32_t bytes) {
  asm volatile("mbarrier.arrive.expect_tx.shared::cta.b64 _, [%0], %1;" ::"r"(bar), "r"(bytes) : "memory");
}
__device__ __forceinline__ void mbar_arrive(uint32_t bar) {
  asm volatile("mbarrier.arrive.shared::cta.b64 _, [%0];" ::"r"(bar) : "memory");
}
__device__ __forceinline__ void mbar_wait(uint32_t bar, uint32_t parity) {
  uint32_t ok;
  int spins = 0;
  do {
      asm volatile("{\n.reg .pred p;\nmbarrier.try_wait.parity.shared::cta.b64 p, [%1], %2;\nselp.b32 %0, 1, 0, p;\n}"
                   : "=r"(ok) : "r"(bar), "r"(parity) : "memory");
    if (++spins > SPIN_LIMIT) break;
  } while (!ok);
}
__device__ __forceinline__ unsigned flag_read(const unsigned* p) {
  unsigned v;
  asm volatile("ld.relaxed.gpu.global.u32 %0, [%1];" : "=r"(v) : "l"(p) : "memory");
  return v;
}
__device__ __forceinline__ void flag_poll(const unsigned* p, unsigned target) {
  unsigned v;
  int spins = 0;
  do {
    asm volatile("ld.relaxed.gpu.global.u32 %0, [%1];" : "=r"(v) : "l"(p) : "memory");
    if (++spins > SPIN_LIMIT) break;
  } while ((int)(v - target) < 0);
}
__device__ __forceinline__ void flag_wait(const unsigned* p, unsigned target) {
  flag_poll(p, target);
}
__device__ __forceinline__ void flag_signal(unsigned* p, int n, int lane) {
  if (lane == 0) asm volatile("fence.release.gpu;" ::: "memory");
  __syncwarp();
  if (lane < n) asm volatile("red.relaxed.gpu.global.add.u32 [%0], 1;" ::"l"(p + 32 * lane) : "memory");
}
__device__ __forceinline__ void flag_bump(unsigned* p) {
  asm volatile("red.relaxed.gpu.global.add.u32 [%0], 1;" ::"l"(p) : "memory");
}
__device__ __forceinline__ void fence_async_smem() { asm volatile("fence.proxy.async.shared::cta;" ::: "memory"); }
__device__ __forceinline__ void wg_sync(int id) { asm volatile("bar.sync %0, 128;" ::"r"(id) : "memory"); }

__device__ __forceinline__ void tma_2d(uint32_t dst, const CUtensorMap* tm, int c0, int c1, uint32_t bar) {
  asm volatile("cp.async.bulk.tensor.2d.shared::cluster.global.mbarrier::complete_tx::bytes [%0], [%1, {%3, %4}], [%2];"
               ::"r"(dst), "l"(tm), "r"(bar), "r"(c0), "r"(c1) : "memory");
}
__device__ __forceinline__ void tma_3d(uint32_t dst, const CUtensorMap* tm, int c0, int c1, int c2, uint32_t bar) {
  asm volatile("cp.async.bulk.tensor.3d.shared::cluster.global.mbarrier::complete_tx::bytes [%0], [%1, {%3, %4, %5}], [%2];"
               ::"r"(dst), "l"(tm), "r"(bar), "r"(c0), "r"(c1), "r"(c2) : "memory");
}
__device__ __forceinline__ void bulk_load(uint32_t dst, const void* src, uint32_t bytes, uint32_t bar) {
  asm volatile("cp.async.bulk.shared::cluster.global.mbarrier::complete_tx::bytes [%0], [%1], %2, [%3];"
               ::"r"(dst), "l"(src), "r"(bytes), "r"(bar) : "memory");
}
__device__ __forceinline__ void bulk_store(void* dst, uint32_t src, uint32_t bytes) {
  asm volatile("cp.async.bulk.global.shared::cta.bulk_group [%0], [%1], %2;" ::"l"(dst), "r"(src), "r"(bytes) : "memory");
}
__device__ __forceinline__ void bulk_wait_read() {
  asm volatile("cp.async.bulk.commit_group;\ncp.async.bulk.wait_group.read 0;" ::: "memory");
}

__device__ __forceinline__ void publish(void* dst, uint32_t src, uint32_t bytes) {
  bulk_store(dst, src, bytes);
  bulk_wait_read();
}

__device__ __forceinline__ void wg_fence() { asm volatile("wgmma.fence.sync.aligned;" ::: "memory"); }
__device__ __forceinline__ void wg_commit() { asm volatile("wgmma.commit_group.sync.aligned;" ::: "memory"); }
template <int N> __device__ __forceinline__ void wg_wait() { asm volatile("wgmma.wait_group.sync.aligned %0;" ::"n"(N) : "memory"); }
__device__ __forceinline__ uint32_t desc_lo(uint32_t addr, uint32_t lbo) { return ((addr & 0x3FFFF) >> 4) | ((lbo >> 4) << 16); }
constexpr uint32_t desc_hi(uint32_t sbo, uint32_t swz) { return (sbo >> 4) | (swz << 30); }
constexpr uint32_t HI_SW128 = desc_hi(1024, 1), HI_SW64 = desc_hi(512, 2), HI_SW32 = desc_hi(256, 3), HI_NONE = desc_hi(128, 0);
template <int N> __device__ __forceinline__ void pin(float* d) {
#pragma unroll
  for (int i = 0; i < N; i++) asm volatile("" : "+f"(d[i])::"memory");
}

__device__ __forceinline__ uint32_t lds32(uint32_t a) {
  uint32_t v;
  asm volatile("ld.volatile.shared.u32 %0, [%1];" : "=r"(v) : "r"(a) : "memory");
  return v;
}
__device__ __forceinline__ uint2 ldg64(const void* a) {
  uint2 v;
  asm volatile("ld.global.nc.v2.u32 {%0, %1}, [%2];" : "=r"(v.x), "=r"(v.y) : "l"(a) : "memory");
  return v;
}
__device__ __forceinline__ void ldsm4(uint32_t* r, uint32_t a) {
  asm volatile("ldmatrix.sync.aligned.m8n8.x4.shared.b16 {%0, %1, %2, %3}, [%4];"
               : "=r"(r[0]), "=r"(r[1]), "=r"(r[2]), "=r"(r[3]) : "r"(a) : "memory");
}
__device__ __forceinline__ void ldsm4t(uint32_t* r, uint32_t a) {
  asm volatile("ldmatrix.sync.aligned.m8n8.x4.trans.shared.b16 {%0, %1, %2, %3}, [%4];"
               : "=r"(r[0]), "=r"(r[1]), "=r"(r[2]), "=r"(r[3]) : "r"(a) : "memory");
}
__device__ __forceinline__ uint2 lds64(uint32_t a) {
  uint2 v;
  asm volatile("ld.shared.v2.u32 {%0, %1}, [%2];" : "=r"(v.x), "=r"(v.y) : "r"(a) : "memory");
  return v;
}
__device__ __forceinline__ uint4 lds128(uint32_t a) {
  uint4 v;
  asm volatile("ld.shared.v4.u32 {%0, %1, %2, %3}, [%4];" : "=r"(v.x), "=r"(v.y), "=r"(v.z), "=r"(v.w) : "r"(a) : "memory");
  return v;
}
__device__ __forceinline__ void sts128(uint32_t a, uint32_t x, uint32_t y, uint32_t z, uint32_t w) {
  asm volatile("st.shared.v4.u32 [%0], {%1, %2, %3, %4};" ::"r"(a), "r"(x), "r"(y), "r"(z), "r"(w) : "memory");
}
__device__ __forceinline__ void stsm4(uint32_t a, const uint32_t* r) {
  asm volatile("stmatrix.sync.aligned.m8n8.x4.shared.b16 [%0], {%1, %2, %3, %4};" ::"r"(a), "r"(r[0]), "r"(r[1]), "r"(r[2]), "r"(r[3]) : "memory");
}
__device__ __forceinline__ uint32_t pack2(float lo, float hi) {
  uint32_t r;
  asm("cvt.rn.bf16x2.f32 %0, %1, %2;" : "=r"(r) : "f"(hi), "f"(lo));
  return r;
}
__device__ __forceinline__ uint32_t movm(uint32_t a) {
  uint32_t d;
  asm volatile("movmatrix.sync.aligned.m8n8.trans.b16 %0, %1;" : "=r"(d) : "r"(a));
  return d;
}
__device__ __forceinline__ uint32_t bmul(uint32_t a, uint32_t b) {
  uint32_t d;
  asm("mul.rn.bf16x2 %0, %1, %2;" : "=r"(d) : "r"(a), "r"(b));
  return d;
}
__device__ __forceinline__ uint32_t badd(uint32_t a, uint32_t b) {
  uint32_t d;
  asm("add.rn.bf16x2 %0, %1, %2;" : "=r"(d) : "r"(a), "r"(b));
  return d;
}
__device__ __forceinline__ uint32_t bfma(uint32_t a, uint32_t b, uint32_t c) {
  uint32_t d;
  asm("fma.rn.bf16x2 %0, %1, %2, %3;" : "=r"(d) : "r"(a), "r"(b), "r"(c));
  return d;
}
__device__ __forceinline__ float bf_lo(uint32_t x) { return __uint_as_float(x << 16); }
__device__ __forceinline__ float bf_hi(uint32_t x) { return __uint_as_float(x & 0xFFFF0000u); }
__device__ __forceinline__ float ex2(float x) {
  float y;
  asm("ex2.approx.ftz.f32 %0, %1;" : "=f"(y) : "f"(x));
  return y;
}
__device__ __forceinline__ float rcp(float x) {
  float y;
  asm("rcp.approx.ftz.f32 %0, %1;" : "=f"(y) : "f"(x));
  return y;
}
__device__ __forceinline__ void mma16816(float* d, uint32_t a0, uint32_t a1, uint32_t a2, uint32_t a3, uint32_t b0, uint32_t b1) {
  asm volatile("mma.sync.aligned.m16n8k16.row.col.f32.bf16.bf16.f32 {%0, %1, %2, %3}, {%4, %5, %6, %7}, {%8, %9}, {%0, %1, %2, %3};"
               : "+f"(d[0]), "+f"(d[1]), "+f"(d[2]), "+f"(d[3])
               : "r"(a0), "r"(a1), "r"(a2), "r"(a3), "r"(b0), "r"(b1));
}
__device__ __forceinline__ void mma1688(float* d, uint32_t a0, uint32_t a1, uint32_t b0) {
  asm volatile("mma.sync.aligned.m16n8k8.row.col.f32.bf16.bf16.f32 {%0, %1, %2, %3}, {%4, %5}, {%6}, {%0, %1, %2, %3};"
               : "+f"(d[0]), "+f"(d[1]), "+f"(d[2]), "+f"(d[3])
               : "r"(a0), "r"(a1), "r"(b0));
}

template <int N> struct WgRS;
template <int N> struct WgSST;
template <> struct WgRS<32> {
  template <uint32_t HB>
  static __device__ __forceinline__ void mma(float* d, const uint32_t* a, uint32_t db) {
    asm volatile("{\n.reg .pred p;\n.reg .b64 db;\nsetp.ne.b32 p, %22, 0;\n"
      "mov.b64 db, {%20, %21};\n"
      "wgmma.mma_async.sync.aligned.m64n32k16.f32.bf16.bf16 {"
      "%0, %1, %2, %3, %4, %5, %6, %7, %8, %9, %10, %11, %12, %13, %14, %15"
      "}, {%16, %17, %18, %19}, db, p, 1, 1, 1;\n}\n"
      : "+f"(d[0]), "+f"(d[1]), "+f"(d[2]), "+f"(d[3]), "+f"(d[4]), "+f"(d[5]), "+f"(d[6]), "+f"(d[7]),
        "+f"(d[8]), "+f"(d[9]), "+f"(d[10]), "+f"(d[11]), "+f"(d[12]), "+f"(d[13]), "+f"(d[14]), "+f"(d[15])
      : "r"(a[0]), "r"(a[1]), "r"(a[2]), "r"(a[3]), "r"(db), "n"(HB), "n"(1));
  }
  template <uint32_t HB>
  static __device__ __forceinline__ void set(float* d, const uint32_t* a, uint32_t db) {
    asm volatile("{\n.reg .pred p;\n.reg .b64 db;\nsetp.ne.b32 p, %22, 0;\n"
      "mov.b64 db, {%20, %21};\n"
      "wgmma.mma_async.sync.aligned.m64n32k16.f32.bf16.bf16 {"
      "%0, %1, %2, %3, %4, %5, %6, %7, %8, %9, %10, %11, %12, %13, %14, %15"
      "}, {%16, %17, %18, %19}, db, p, 1, 1, 1;\n}\n"
      : "=f"(d[0]), "=f"(d[1]), "=f"(d[2]), "=f"(d[3]), "=f"(d[4]), "=f"(d[5]), "=f"(d[6]), "=f"(d[7]),
        "=f"(d[8]), "=f"(d[9]), "=f"(d[10]), "=f"(d[11]), "=f"(d[12]), "=f"(d[13]), "=f"(d[14]), "=f"(d[15])
      : "r"(a[0]), "r"(a[1]), "r"(a[2]), "r"(a[3]), "r"(db), "n"(HB), "n"(0));
  }
};
template <> struct WgRS<64> {
  template <uint32_t HB>
  static __device__ __forceinline__ void mma(float* d, const uint32_t* a, uint32_t db) {
    asm volatile("{\n.reg .pred p;\n.reg .b64 db;\nsetp.ne.b32 p, %38, 0;\n"
      "mov.b64 db, {%36, %37};\n"
      "wgmma.mma_async.sync.aligned.m64n64k16.f32.bf16.bf16 {"
      "%0, %1, %2, %3, %4, %5, %6, %7, %8, %9, %10, %11, %12, %13, %14, %15, "
      "%16, %17, %18, %19, %20, %21, %22, %23, %24, %25, %26, %27, %28, %29, %30, %31"
      "}, {%32, %33, %34, %35}, db, p, 1, 1, 1;\n}\n"
      : "+f"(d[0]), "+f"(d[1]), "+f"(d[2]), "+f"(d[3]), "+f"(d[4]), "+f"(d[5]), "+f"(d[6]), "+f"(d[7]),
        "+f"(d[8]), "+f"(d[9]), "+f"(d[10]), "+f"(d[11]), "+f"(d[12]), "+f"(d[13]), "+f"(d[14]), "+f"(d[15]),
        "+f"(d[16]), "+f"(d[17]), "+f"(d[18]), "+f"(d[19]), "+f"(d[20]), "+f"(d[21]), "+f"(d[22]), "+f"(d[23]),
        "+f"(d[24]), "+f"(d[25]), "+f"(d[26]), "+f"(d[27]), "+f"(d[28]), "+f"(d[29]), "+f"(d[30]), "+f"(d[31])
      : "r"(a[0]), "r"(a[1]), "r"(a[2]), "r"(a[3]), "r"(db), "n"(HB), "n"(1));
  }
  template <uint32_t HB>
  static __device__ __forceinline__ void set(float* d, const uint32_t* a, uint32_t db) {
    asm volatile("{\n.reg .pred p;\n.reg .b64 db;\nsetp.ne.b32 p, %38, 0;\n"
      "mov.b64 db, {%36, %37};\n"
      "wgmma.mma_async.sync.aligned.m64n64k16.f32.bf16.bf16 {"
      "%0, %1, %2, %3, %4, %5, %6, %7, %8, %9, %10, %11, %12, %13, %14, %15, "
      "%16, %17, %18, %19, %20, %21, %22, %23, %24, %25, %26, %27, %28, %29, %30, %31"
      "}, {%32, %33, %34, %35}, db, p, 1, 1, 1;\n}\n"
      : "=f"(d[0]), "=f"(d[1]), "=f"(d[2]), "=f"(d[3]), "=f"(d[4]), "=f"(d[5]), "=f"(d[6]), "=f"(d[7]),
        "=f"(d[8]), "=f"(d[9]), "=f"(d[10]), "=f"(d[11]), "=f"(d[12]), "=f"(d[13]), "=f"(d[14]), "=f"(d[15]),
        "=f"(d[16]), "=f"(d[17]), "=f"(d[18]), "=f"(d[19]), "=f"(d[20]), "=f"(d[21]), "=f"(d[22]), "=f"(d[23]),
        "=f"(d[24]), "=f"(d[25]), "=f"(d[26]), "=f"(d[27]), "=f"(d[28]), "=f"(d[29]), "=f"(d[30]), "=f"(d[31])
      : "r"(a[0]), "r"(a[1]), "r"(a[2]), "r"(a[3]), "r"(db), "n"(HB), "n"(0));
  }
};
template <> struct WgSST<48> {
  template <uint32_t HA, uint32_t HB>
  static __device__ __forceinline__ void mma(float* d, uint32_t da, uint32_t db, int sc) {
    asm volatile("{\n.reg .pred p;\n.reg .b64 da, db;\nsetp.ne.b32 p, %28, 0;\n"
      "mov.b64 da, {%24, %25};\nmov.b64 db, {%26, %27};\n"
      "wgmma.mma_async.sync.aligned.m64n48k16.f32.bf16.bf16 {"
      "%0, %1, %2, %3, %4, %5, %6, %7, %8, %9, %10, %11, %12, %13, %14, %15, "
      "%16, %17, %18, %19, %20, %21, %22, %23"
      "}, da, db, p, 1, 1, 0, 1;\n}\n"
      : "+f"(d[0]), "+f"(d[1]), "+f"(d[2]), "+f"(d[3]), "+f"(d[4]), "+f"(d[5]), "+f"(d[6]), "+f"(d[7]),
        "+f"(d[8]), "+f"(d[9]), "+f"(d[10]), "+f"(d[11]), "+f"(d[12]), "+f"(d[13]), "+f"(d[14]), "+f"(d[15]),
        "+f"(d[16]), "+f"(d[17]), "+f"(d[18]), "+f"(d[19]), "+f"(d[20]), "+f"(d[21]), "+f"(d[22]), "+f"(d[23])
      : "r"(da), "n"(HA), "r"(db), "n"(HB), "r"(sc));
  }
};
template <> struct WgSST<80> {
  template <uint32_t HA, uint32_t HB>
  static __device__ __forceinline__ void mma(float* d, uint32_t da, uint32_t db, int sc) {
    asm volatile("{\n.reg .pred p;\n.reg .b64 da, db;\nsetp.ne.b32 p, %44, 0;\n"
      "mov.b64 da, {%40, %41};\nmov.b64 db, {%42, %43};\n"
      "wgmma.mma_async.sync.aligned.m64n80k16.f32.bf16.bf16 {"
      "%0, %1, %2, %3, %4, %5, %6, %7, %8, %9, %10, %11, %12, %13, %14, %15, "
      "%16, %17, %18, %19, %20, %21, %22, %23, %24, %25, %26, %27, %28, %29, %30, %31, "
      "%32, %33, %34, %35, %36, %37, %38, %39"
      "}, da, db, p, 1, 1, 0, 1;\n}\n"
      : "+f"(d[0]), "+f"(d[1]), "+f"(d[2]), "+f"(d[3]), "+f"(d[4]), "+f"(d[5]), "+f"(d[6]), "+f"(d[7]),
        "+f"(d[8]), "+f"(d[9]), "+f"(d[10]), "+f"(d[11]), "+f"(d[12]), "+f"(d[13]), "+f"(d[14]), "+f"(d[15]),
        "+f"(d[16]), "+f"(d[17]), "+f"(d[18]), "+f"(d[19]), "+f"(d[20]), "+f"(d[21]), "+f"(d[22]), "+f"(d[23]),
        "+f"(d[24]), "+f"(d[25]), "+f"(d[26]), "+f"(d[27]), "+f"(d[28]), "+f"(d[29]), "+f"(d[30]), "+f"(d[31]),
        "+f"(d[32]), "+f"(d[33]), "+f"(d[34]), "+f"(d[35]), "+f"(d[36]), "+f"(d[37]), "+f"(d[38]), "+f"(d[39])
      : "r"(da), "n"(HA), "r"(db), "n"(HB), "r"(sc));
  }
};
template <> struct WgSST<192> {
  template <uint32_t HA, uint32_t HB>
  static __device__ __forceinline__ void mma(float* d, uint32_t da, uint32_t db, int sc) {
    asm volatile("{\n.reg .pred p;\n.reg .b64 da, db;\nsetp.ne.b32 p, %100, 0;\n"
      "mov.b64 da, {%96, %97};\nmov.b64 db, {%98, %99};\n"
      "wgmma.mma_async.sync.aligned.m64n192k16.f32.bf16.bf16 {"
      "%0, %1, %2, %3, %4, %5, %6, %7, %8, %9, %10, %11, %12, %13, %14, %15, "
      "%16, %17, %18, %19, %20, %21, %22, %23, %24, %25, %26, %27, %28, %29, %30, %31, "
      "%32, %33, %34, %35, %36, %37, %38, %39, %40, %41, %42, %43, %44, %45, %46, %47, "
      "%48, %49, %50, %51, %52, %53, %54, %55, %56, %57, %58, %59, %60, %61, %62, %63, "
      "%64, %65, %66, %67, %68, %69, %70, %71, %72, %73, %74, %75, %76, %77, %78, %79, "
      "%80, %81, %82, %83, %84, %85, %86, %87, %88, %89, %90, %91, %92, %93, %94, %95"
      "}, da, db, p, 1, 1, 0, 1;\n}\n"
      : "+f"(d[0]), "+f"(d[1]), "+f"(d[2]), "+f"(d[3]), "+f"(d[4]), "+f"(d[5]), "+f"(d[6]), "+f"(d[7]),
        "+f"(d[8]), "+f"(d[9]), "+f"(d[10]), "+f"(d[11]), "+f"(d[12]), "+f"(d[13]), "+f"(d[14]), "+f"(d[15]),
        "+f"(d[16]), "+f"(d[17]), "+f"(d[18]), "+f"(d[19]), "+f"(d[20]), "+f"(d[21]), "+f"(d[22]), "+f"(d[23]),
        "+f"(d[24]), "+f"(d[25]), "+f"(d[26]), "+f"(d[27]), "+f"(d[28]), "+f"(d[29]), "+f"(d[30]), "+f"(d[31]),
        "+f"(d[32]), "+f"(d[33]), "+f"(d[34]), "+f"(d[35]), "+f"(d[36]), "+f"(d[37]), "+f"(d[38]), "+f"(d[39]),
        "+f"(d[40]), "+f"(d[41]), "+f"(d[42]), "+f"(d[43]), "+f"(d[44]), "+f"(d[45]), "+f"(d[46]), "+f"(d[47]),
        "+f"(d[48]), "+f"(d[49]), "+f"(d[50]), "+f"(d[51]), "+f"(d[52]), "+f"(d[53]), "+f"(d[54]), "+f"(d[55]),
        "+f"(d[56]), "+f"(d[57]), "+f"(d[58]), "+f"(d[59]), "+f"(d[60]), "+f"(d[61]), "+f"(d[62]), "+f"(d[63]),
        "+f"(d[64]), "+f"(d[65]), "+f"(d[66]), "+f"(d[67]), "+f"(d[68]), "+f"(d[69]), "+f"(d[70]), "+f"(d[71]),
        "+f"(d[72]), "+f"(d[73]), "+f"(d[74]), "+f"(d[75]), "+f"(d[76]), "+f"(d[77]), "+f"(d[78]), "+f"(d[79]),
        "+f"(d[80]), "+f"(d[81]), "+f"(d[82]), "+f"(d[83]), "+f"(d[84]), "+f"(d[85]), "+f"(d[86]), "+f"(d[87]),
        "+f"(d[88]), "+f"(d[89]), "+f"(d[90]), "+f"(d[91]), "+f"(d[92]), "+f"(d[93]), "+f"(d[94]), "+f"(d[95])
      : "r"(da), "n"(HA), "r"(db), "n"(HB), "r"(sc));
  }
};

struct FftConst {
  uint32_t f[2][4], fi[4][4];
  uint32_t ta[2][2], tb[2][2];
};
__device__ __forceinline__ void cis(int m, float scale, float& c, float& s) {
  const float a = (float)m * (-6.283185307179586f * scale);
  c = __cosf(a);
  s = __sinf(a);
}
__device__ __forceinline__ void fft_tables(uint32_t (&v)[12], int tw) {
  const int row = tw >> 2, ch = tw & 3;
#pragma unroll
  for (int i = 0; i < 4; i++) {
    float c[2], s[2], x[2];
#pragma unroll
    for (int e = 0; e < 2; e++) {
      cis((((32 * (8 * ch + 2 * i + e) + 15) * (4 * row - 63) + 2048) & 4095) - 2048, 1.f / 4096, c[e], s[e]);
      float gc, gs;
      cis((((row & 15) * (8 * (ch & 1) + 2 * i + e) + 8) & 15) - 8, 1.f / 16, gc, gs);
      x[e] = (row >> 4) == (ch >> 1) ? gc : (ch >> 1) ? gs : -gs;
    }
    v[i] = pack2(c[0] * 0.125f, c[1] * 0.125f);
    v[4 + i] = pack2(s[0] * 0.125f, s[1] * 0.125f);
    v[8 + i] = pack2(x[0], x[1]);
  }
#pragma unroll
  for (int i = 0; i < 12; i++) asm volatile("" : "+r"(v[i]));
}
__device__ __forceinline__ void fft_tables_store(const uint32_t (&v)[12], uint32_t sb, int tw) {
  const int row = tw >> 2;
  const uint32_t x = ((tw ^ (row >> 1)) & 3) << 4, a = sb + OFF_FT + (16 * (row >> 3) + (row & 7)) * 64 + x;
  sts128(a, v[0], v[1], v[2], v[3]);
  sts128(a + 512, v[4], v[5], v[6], v[7]);
  sts128(sb + OFF_GT + row * 64 + x, v[8], v[9], v[10], v[11]);
}
__device__ __forceinline__ void fft_twiddles(uint32_t (&v)[2], int tw) {
  float a[2], s[2];
#pragma unroll
  for (int i = 0; i < 2; i++) {
    float c;
    cis((2 * (2 * (tw & 3) + i) - 15) * (4 * (tw >> 2) - 63), 1.f / 4096, c, s[i]);
    a[i] = __fdividef(-s[i], 1.f + c);
  }
  v[0] = pack2(a[0], a[1]);
  v[1] = pack2(s[0], s[1]);
  asm volatile("" : "+r"(v[0]), "+r"(v[1]));
}
__device__ __forceinline__ void fft_matrices(FftConst& k, uint32_t sb, int w, int lane) {
  const uint32_t x = (lane >> 1) & 3;
  const uint2 t0 = lds64(sb + OFF_TT + 256 * w + 8 * lane), t1 = lds64(sb + OFF_TT + 256 * w + 8 * (lane ^ 3));
  k.ta[0][0] = t0.x;
  k.tb[0][0] = t0.y;
  k.ta[1][1] = __byte_perm(t1.x, 0, 0x1032);
  k.tb[1][1] = __byte_perm(t1.y, 0, 0x1032);
#pragma unroll
  for (int j = 0; j < 2; j++) {
    k.ta[1 - j][j] = k.ta[j][j] ^ 0x80008000u;
    k.tb[1 - j][j] = k.tb[j][j] ^ 0x80008000u;
    asm volatile("" : "+r"(k.ta[0][j]), "+r"(k.tb[0][j]), "+r"(k.ta[1][j]), "+r"(k.tb[1][j]));
  }
#pragma unroll
  for (int i = 0; i < 2; i++) {
    ldsm4(k.f[i], sb + OFF_FT + (16 * w + (lane & 15)) * 64 + (((2 * i + (lane >> 4)) ^ x) << 4));
    ldsm4t(k.fi[i], sb + OFF_FT + (32 * i + lane) * 64 + ((w ^ x) << 4));
#pragma unroll
    for (int j = 0; j < 4; j++) {
      k.fi[2 + i][j] = (j & 1) ? k.fi[i][j - 1] ^ 0x80008000u : k.fi[i][j + 1];
      asm volatile("" : "+r"(k.fi[2 + i][j]));
    }
  }
}
__device__ __forceinline__ void rot(uint32_t& x, uint32_t& y, uint32_t a, uint32_t b) {
  x = bfma(a, y, x);
  y = bfma(b, x, y);
  x = bfma(a, y, x);
}
__device__ __forceinline__ void twiddle_fwd(uint32_t (&a)[4][4], float* d, const FftConst& k) {
#pragma unroll
  for (int q = 0; q < 4; q++)
#pragma unroll
    for (int j = 0; j < 2; j++) {
      const float* x = d + 8 * q + 4 * j;
      uint32_t re = pack2(x[0], x[1]), im = pack2(x[2], x[3]);
      rot(re, im, k.ta[0][j], k.tb[0][j]);
      a[q & 2][2 * j + (q & 1)] = re;
      a[(q & 2) + 1][2 * j + (q & 1)] = im;
    }
}
__device__ __forceinline__ void g_step(float* d, const uint32_t (&a)[4][4], uint32_t dre, uint32_t dim) {
  WgRS<32>::set<HI_SW64>(d, a[0], dre);
  WgRS<32>::set<HI_SW64>(d + 16, a[2], dre);
  WgRS<32>::mma<HI_SW64>(d, a[1], dim);
  WgRS<32>::mma<HI_SW64>(d + 16, a[3], dim);
  wg_commit();
}

__device__ __forceinline__ void products(uint32_t (&a)[4][4], const float* H, const float* U, int p) {
#pragma unroll
  for (int j = 0; j < 2; j++)
#pragma unroll
    for (int m = 2 * p; m < 2 * p + 2; m++) {
      float pr[2], pi[2];
#pragma unroll
      for (int x = 0; x < 2; x++)
#pragma unroll
        for (int q = 0; q <= m; q++) {
          const int ih = 16 * (q >> 1) + 2 * (q & 1) + 4 * j + x, iu = 16 * ((m - q) >> 1) + 2 * ((m - q) & 1) + 4 * j + x;
          pr[x] = q ? fmaf(H[ih], U[iu], pr[x]) : H[ih] * U[iu];
          pi[x] = q ? fmaf(H[ih], U[iu + 8], pi[x]) : H[ih] * U[iu + 8];
          pr[x] = fmaf(-H[ih + 8], U[iu + 8], pr[x]);
          pi[x] = fmaf(H[ih + 8], U[iu], pi[x]);
        }
      a[m & 2][2 * j + (m & 1)] = pack2(pr[0], pr[1]);
      a[(m & 2) + 1][2 * j + (m & 1)] = pack2(pi[0], pi[1]);
    }
}

__device__ __forceinline__ void conv_channel(const FftConst& k, uint32_t sb, int c, int wg, int w, int lane) {
  const uint32_t cb = sb + off_ch(c), bars = sb + OFF_BAR;
  const uint32_t du = desc_lo(cb, 1024), dg = desc_lo(sb + OFF_GT, 16), dz = desc_lo(cb + U_BYTES, 16);
  float U[32], H[32];
  uint32_t a[4][4], e[4][4];
  const float dv = __uint_as_float(lds32(sb + OFF_D + 4 * c));
  wg_fence();
  WgRS<64>::set<HI_SW32>(H, k.f[0], du + 256);
  WgRS<64>::mma<HI_SW32>(H, k.f[1], du + 256 + 32);
  wg_commit();
  wg_wait<0>();
  pin<32>(H);
  twiddle_fwd(a, H, k);
  mbar_wait(bars + 8 * (B_U + (c < 3 ? c : 3)), 0);
  TSM(w == 0 && c < 3, 7 + wg);
  wg_fence();
  WgRS<64>::set<HI_SW32>(U, k.f[0], du);
  WgRS<64>::mma<HI_SW32>(U, k.f[1], du + 32);
  wg_commit();
  g_step(H, a, dg, dg + 64);
  wg_wait<1>();
  pin<32>(U);
  twiddle_fwd(e, U, k);
  wg_fence();
  g_step(U, e, dg, dg + 64);
  wg_wait<0>();
  pin<32>(U);
  pin<32>(H);
#pragma unroll
  for (int j = 0; j < 4; j++) H[4 * (j >> 1) + (j & 1)] += dv;
  float V[32];
#pragma unroll
  for (int p = 0; p < 2; p++) {
    products(a, H, U, p);
    wg_fence();
    WgRS<32>::set<HI_SW64>(V + 16 * p, a[2 * p], dg + 64);
    WgRS<32>::mma<HI_SW64>(V + 16 * p, a[2 * p + 1], dg);
    wg_commit();
  }
  const uint32_t za = cb + U_BYTES + (8 * w + (lane & 7)) * 128 + (((lane >> 3) ^ (lane & 7)) << 4);
  const uint32_t ya = cb + (lane >> 4) * 1024 + (8 * w + (lane & 7)) * 32 + ((((lane >> 3) ^ (lane >> 2)) & 1) << 4);
  wg_sync(1 + wg);
#pragma unroll
  for (int p = 0; p < 2; p++) {
    if (p == 0) wg_wait<1>();
    else wg_wait<0>();
    pin<16>(V + 16 * p);
#pragma unroll
    for (int i = 0; i < 4; i++) {
      const int j = i & 1;
      const float* x = V + 16 * p + 4 * j + (i & 2);
      e[p][i] = pack2(x[8], x[9]);
      e[2 + p][i] = pack2(x[0], x[1]);
      rot(e[p][i], e[2 + p][i], k.ta[1][j], k.tb[1][j]);
    }
    stsm4(za ^ (64 * p), e[p]);
    stsm4((za ^ (64 * p)) + 4096, e[2 + p]);
  }
  fence_async_smem();
  wg_sync(1 + wg);
  wg_fence();
  WgRS<64>::set<HI_SW128>(H, k.fi[0], dz);
#pragma unroll
  for (int ks = 1; ks < 4; ks++) WgRS<64>::mma<HI_SW128>(H, k.fi[ks], dz + 128 * ks);
  wg_commit();
  wg_wait<0>();
  pin<32>(H);
  if (lane == 0) mbar_arrive(bars + 8 * B_CVD);
  TSIF(w == 0, 88 + c);
#pragma unroll
  for (int j = 0; j < 8; j++)
    a[j >> 2][j & 3] = j < 2 ? pack2(H[4 * j], H[4 * j + 1]) : pack2(H[4 * j] + H[4 * j - 6], H[4 * j + 1] + H[4 * j - 5]);
  stsm4(ya, a[0]);
  stsm4(ya + 2048, a[1]);
  fence_async_smem();
  __syncwarp();
}

__device__ __forceinline__ void prep_slab(uint4* res, const uint2* sw, uint32_t sb, int slab, int w, int lane) {
  const int t = lane & 3, tp = (lane & 7) >> 1, pos = 8 * tp + 2 * (((lane >> 3) + tp) & 3) + (lane & 1);
  const uint32_t base = sb + OFF_KVS + slab * KVS_BYTES + pos * 128;
  uint32_t kk[2][4][4], vv[2][4];
  mbar_wait(sb + OFF_BAR + 8 * (B_KV + slab), 0);
#pragma unroll
  for (int h = 0; h < 2; h++) {
#pragma unroll
    for (int j = 0; j < 4; j++) {
      const uint32_t a = base + 128 * j;
      ldsm4t(kk[h][j], a + (((w + 4 * h) ^ ((a >> 7) & 7)) << 4));
    }
    const uint32_t a = base + KVS_V;
    ldsm4t(vv[h], a + (((w + 4 * h) ^ ((a >> 7) & 7)) << 4));
  }
#pragma unroll
  for (int h = 0; h < 2; h++) {
    uint32_t (&k)[4][4] = kk[h];
    uint32_t (&v)[4] = vv[h];
    const uint32_t w0 = __byte_perm(sw[h].x, 0, 0x1010), w1 = __byte_perm(sw[h].x, 0, 0x3232);
    const uint32_t w2 = __byte_perm(sw[h].y, 0, 0x1010), w3 = __byte_perm(sw[h].y, 0, 0x3232);
#pragma unroll
    for (int m = 0; m < 4; m++)
      v[m] = bmul(badd(badd(badd(bmul(k[0][m], w3), bmul(k[1][m], w2)), bmul(k[2][m], w1)), bmul(k[3][m], w0)), v[m]);
    uint32_t a[4];
#pragma unroll
    for (int m = 0; m < 4; m++) a[m] = (t & 1) ? v[(m + 3) & 3] : v[m];
    res[h] = (t & 2) ? make_uint4(a[2], a[3], a[0], a[1]) : make_uint4(a[0], a[1], a[2], a[3]);
  }
}

__device__ __forceinline__ void prep_gate(const Params& p, uint32_t sb, int b, int w, int lane) {
  uint2 gw[5], x[4][5];
#pragma unroll
  for (int j = 0; j < 5; j++) gw[j] = ldg64(reinterpret_cast<const uint2*>(p.gate_w) + lane + 32 * j);
#pragma unroll
  for (int i = 0; i < 4; i++)
#pragma unroll
    for (int j = 0; j < 5; j++)
      x[i][j] = ldg64(reinterpret_cast<const uint2*>(p.q) + (16 * b + 4 * w + i) * (DIM / 4) + lane + 32 * j);
  float s[4];
#pragma unroll
  for (int i = 0; i < 4; i++) {
    s[i] = 0.f;
#pragma unroll
    for (int j = 0; j < 5; j++) {
      const uint32_t m0 = bmul(x[i][j].x, gw[j].x), m1 = bmul(x[i][j].y, gw[j].y);
      s[i] += (bf_lo(m0) + bf_hi(m0)) + (bf_lo(m1) + bf_hi(m1));
    }
  }
  const bool h = lane & 16, q = lane & 8;
  const float a = (h ? s[2] : s[0]) + __shfl_xor_sync(0xffffffffu, h ? s[0] : s[2], 16);
  const float c = (h ? s[3] : s[1]) + __shfl_xor_sync(0xffffffffu, h ? s[1] : s[3], 16);
  float z = (q ? c : a) + __shfl_xor_sync(0xffffffffu, q ? a : c, 8);
#pragma unroll
  for (int o = 4; o > 0; o >>= 1) z += __shfl_xor_sync(0xffffffffu, z, o);
  z = bf_lo(pack2(z, 0.f));
  z = bf_lo(pack2(__fdividef(1.f, 1.f + __expf(-z)), 0.f));
  mbar_wait(sb + OFF_BAR + 8 * B_S3, 0);
  if ((lane & 7) == 0) asm volatile("st.shared.f32 [%0], %1;" ::"r"(sb + OFF_GATE + 64 * (b & 7) + 16 * w + (lane >> 1)), "f"(z) : "memory");
  fence_async_smem();
}

__device__ __forceinline__ uint32_t bmax(uint32_t a, uint32_t b) {
  uint32_t d;
  asm("max.bf16x2 %0, %1, %2;" : "=r"(d) : "r"(a), "r"(b));
  return d;
}
__device__ __forceinline__ void softmax_two(const float (&l)[2][2], uint32_t& p0, uint32_t& p1) {
  constexpr float kScale = 0.22360679774997896f, kLog2e = 1.4426950408889634f;
  const uint32_t r0 = pack2(l[0][0], l[1][0]), r1 = pack2(l[0][1], l[1][1]);
  const uint32_t x0 = pack2(bf_lo(r0) * kScale, bf_hi(r0) * kScale), x1 = pack2(bf_lo(r1) * kScale, bf_hi(r1) * kScale);
  uint32_t m = bmax(x0, x1);
  m = bmax(m, __shfl_xor_sync(0xffffffffu, m, 1));
  m = bmax(m, __shfl_xor_sync(0xffffffffu, m, 2));
  const float m0 = bf_lo(m) * kLog2e, m1 = bf_hi(m) * kLog2e;
  p0 = pack2(ex2(bf_lo(x0) * kLog2e - m0), ex2(bf_lo(x1) * kLog2e - m0));
  p1 = pack2(ex2(bf_hi(x0) * kLog2e - m1), ex2(bf_hi(x1) * kLog2e - m1));
}

__device__ __forceinline__ void halo_read(uint32_t (&kpv)[10], uint32_t (&vpv)[10], uint32_t (&tg)[7], const uint4* hp) {
#pragma unroll
  for (int j = 0; j < 7; j++) {
    uint32_t x0, x1, x2;
    asm volatile("ld.relaxed.gpu.global.v4.u32 {%0, %1, %2, %3}, [%4];"
                 : "=r"(x0), "=r"(x1), "=r"(x2), "=r"(tg[j]) : "l"(hp + 32 * j) : "memory");
    if (j < 4) kpv[3 * j] = x0; else vpv[3 * j - 10] = x0;
    if (j < 3) kpv[3 * j + 1] = x1; else vpv[3 * j - 9] = x1;
    if (j < 3) kpv[3 * j + 2] = x2; else if (j < 6) vpv[3 * j - 8] = x2;
  }
}

template <int ROT>
__device__ __forceinline__ void pack_qkv(const float* acc, uint32_t (&qlo)[10], uint32_t (&qhi)[10], uint32_t (&klo)[10],
                                         uint32_t (&khi)[10], uint32_t (&vlo)[10], uint32_t (&vhi)[10]) {
#pragma unroll
  for (int j = 0; j < 10; j++) {
    const int x = (j + ROT) % 10, tq = x < 8 ? x : 16 + x, tk = x < 8 ? 8 + x : 18 + x, tv = x < 8 ? 16 + x : 20 + x;
    khi[j] = pack2(acc[4 * tk + 2], acc[4 * tk + 3]);
    vhi[j] = movm(pack2(acc[4 * tv + 2], acc[4 * tv + 3]));
    qlo[j] = pack2(acc[4 * tq], acc[4 * tq + 1]);
    qhi[j] = pack2(acc[4 * tq + 2], acc[4 * tq + 3]);
    klo[j] = pack2(acc[4 * tk], acc[4 * tk + 1]);
    vlo[j] = pack2(acc[4 * tv], acc[4 * tv + 1]);
    asm volatile("" : "+r"(khi[j]), "+r"(qlo[j]), "+r"(qhi[j]), "+r"(klo[j]), "+r"(vlo[j]));
  }
}

template <int ROT> __device__ __forceinline__ void halo_send(const float* acc, uint4* ho, uint32_t tag) {
#pragma unroll
  for (int j = 0; j < 7; j++) {
    uint32_t x[3];
#pragma unroll
    for (int e = 0; e < 3; e++) {
      const int i = 3 * j + e, y = (i % 10 + ROT) % 10, tk = y < 8 ? 8 + y : 18 + y, tv = y < 8 ? 16 + y : 20 + y;
      x[e] = i < 10 ? pack2(acc[4 * tk + 2], acc[4 * tk + 3]) : i < 20 ? movm(pack2(acc[4 * tv + 2], acc[4 * tv + 3])) : 0u;
    }
    asm volatile("st.relaxed.gpu.global.v4.u32 [%0], {%1, %2, %3, %4};" ::"l"(ho + 32 * j), "r"(x[0]), "r"(x[1]), "r"(x[2]), "r"(tag) : "memory");
  }
}

__device__ __forceinline__ void attention(float* acc, uint32_t sb, int b, int par, int w, int lane, uint32_t tag) {
  const int g = lane >> 2, t = lane & 3;
  uint32_t klo[10], khi[10], vlo[10], vhi[10], qlo[10], qhi[10], kpv[10], vpv[10];
  if (w == 3 && b < NCTA - 8) {
    uint4* ho = g_halo + (b * 2 + par) * 224 + lane;
    if (tail_first(b & 7)) halo_send<8>(acc, ho, tag);
    else halo_send<0>(acc, ho, tag);
    TSIF(par == 0, 76);
    pin<120>(acc);
  }
  if (tail_first(b & 7)) pack_qkv<8>(acc, qlo, qhi, klo, khi, vlo, vhi);
  else pack_qkv<0>(acc, qlo, qhi, klo, khi, vlo, vhi);
  const uint32_t xa = sb + OFF_KVX + (par * 3) * 2560 + lane * 16;
  if (w < 3) {
    sts128(xa + w * 2560, khi[0], khi[1], khi[2], khi[3]);
    sts128(xa + w * 2560 + 512, khi[4], khi[5], khi[6], khi[7]);
    sts128(xa + w * 2560 + 1024, khi[8], khi[9], vhi[0], vhi[1]);
    sts128(xa + w * 2560 + 1536, vhi[2], vhi[3], vhi[4], vhi[5]);
    sts128(xa + w * 2560 + 2048, vhi[6], vhi[7], vhi[8], vhi[9]);
  }
  TSIF(par == 0 && w == 1, 64);
#pragma unroll
  for (int j = 0; j < 10; j++) vlo[j] = movm(vlo[j]);
  const bool far0 = 2 * t > g, far1 = 2 * t + 1 > g;
  const uint32_t mfar = (far0 ? 0x0000FFFFu : 0u) | (far1 ? 0xFFFF0000u : 0u);
  float slo[4][2], lg[2][2];
  uint32_t phi[4], plo[4], qml[4], qmh[4];
#pragma unroll
  for (int h = 0; h < 4; h++) {
    const int f = h == 0 ? 0 : h == 1 ? 3 : h == 2 ? 5 : 8, hf = h < 2 ? 2 : 7;
    const bool mine = (h & 1) ? t >= 2 : t < 2;
    qml[h] = mine ? qlo[hf] : 0u;
    qmh[h] = mine ? qhi[hf] : 0u;
    float a[4] = {0.f, 0.f, 0.f, 0.f}, c[4] = {0.f, 0.f, 0.f, 0.f};
    mma16816(a, qlo[f], qhi[f], qlo[f + 1], qhi[f + 1], klo[f], klo[f + 1]);
    mma16816(c, qlo[f], qhi[f], qlo[f + 1], qhi[f + 1], khi[f], khi[f + 1]);
    mma1688(a, qml[h], qmh[h], klo[hf]);
    mma1688(c, qml[h], qmh[h], khi[hf]);
    slo[h][0] = a[0];
    slo[h][1] = a[1];
    lg[h & 1][0] = far0 ? a[2] : c[2];
    lg[h & 1][1] = far1 ? a[3] : c[3];
    if (h & 1) softmax_two(lg, phi[h - 1], phi[h]);
  }
  TSIF(par == 0 && w == 1, 65);
  wg_sync(1 + par);
  TSIF(par == 0 && w == 1, 66);
  const bool nohist = (w == 0) && (b < 8);
  const uint4* hp = g_halo + ((b - 8) * 2 + par) * 224 + lane;
  uint32_t tg[7];
  if (w > 0) {
    const uint4 v0 = lds128(xa + (w - 1) * 2560), v1 = lds128(xa + (w - 1) * 2560 + 512), v2 = lds128(xa + (w - 1) * 2560 + 1024);
    const uint4 v3 = lds128(xa + (w - 1) * 2560 + 1536), v4 = lds128(xa + (w - 1) * 2560 + 2048);
    kpv[0] = v0.x; kpv[1] = v0.y; kpv[2] = v0.z; kpv[3] = v0.w; kpv[4] = v1.x; kpv[5] = v1.y; kpv[6] = v1.z; kpv[7] = v1.w;
    kpv[8] = v2.x; kpv[9] = v2.y; vpv[0] = v2.z; vpv[1] = v2.w; vpv[2] = v3.x; vpv[3] = v3.y; vpv[4] = v3.z; vpv[5] = v3.w;
    vpv[6] = v4.x; vpv[7] = v4.y; vpv[8] = v4.z; vpv[9] = v4.w;
  } else if (nohist) {
#pragma unroll
    for (int j = 0; j < 10; j++) kpv[j] = vpv[j] = 0u;
  } else {
    TSIF(par == 0, 77);
    halo_read(kpv, vpv, tg, hp);
  }
  if (w == 0 && !nohist) {
    int spins = 0;
    while (true) {
      bool ok = true;
#pragma unroll
      for (int j = 0; j < 7; j++) ok = ok && tg[j] == tag;
      if (__all_sync(0xffffffffu, ok) || ++spins > SPIN_LIMIT) break;
      halo_read(kpv, vpv, tg, hp);
    }
    TSIF(par == 0, 79);
  }
#pragma unroll
  for (int h = 0; h < 4; h++) {
    const int f = h == 0 ? 0 : h == 1 ? 3 : h == 2 ? 5 : 8, hf = h < 2 ? 2 : 7;
    float a[4] = {0.f, 0.f, 0.f, 0.f};
    mma16816(a, qlo[f], qhi[f], qlo[f + 1], qhi[f + 1], kpv[f], kpv[f + 1]);
    mma1688(a, qml[h], qmh[h], kpv[hf]);
    const float ninf = __int_as_float(0xff800000);
    lg[h & 1][0] = far0 ? (nohist ? ninf : a[0]) : slo[h][0];
    lg[h & 1][1] = far1 ? (nohist ? ninf : a[1]) : slo[h][1];
    if (h & 1) softmax_two(lg, plo[h - 1], plo[h]);
  }
  TSIF(par == 0 && w <= 1, 67 + w);
  uint32_t ov[20];
#pragma unroll
  for (int hp = 0; hp < 2; hp++) {
    const int hf = hp ? 7 : 2;
    float sh[4] = {0.f, 0.f, 0.f, 0.f}, i0 = 0.f, i1 = 0.f;
#pragma unroll
    for (int e = 0; e < 2; e++) {
      const int h = 2 * hp + e, f = h == 0 ? 0 : h == 1 ? 3 : h == 2 ? 5 : 8;
      const uint32_t a0 = plo[h] & mfar, a2 = plo[h] & ~mfar, a3 = phi[h] & mfar, c1 = phi[h] & ~mfar;
      float sum[4] = {0.f, 0.f, 0.f, 0.f};
      mma1688(sum, plo[h], phi[h], 0x3F803F80u);
      const float r0 = rcp(sum[0]), r1 = rcp(sum[2]);
#pragma unroll
      for (int j = f; j < f + 2; j++) {
        float o[4] = {0.f, 0.f, 0.f, 0.f};
        mma16816(o, a0, 0u, a2, a3, vpv[j], vlo[j]);
        mma1688(o, 0u, c1, vhi[j]);
        ov[2 * j] = pack2(o[0] * r0, o[1] * r0);
        ov[2 * j + 1] = pack2(o[2] * r1, o[3] * r1);
      }
      const bool mine = e ? g >= 4 : g < 4;
      mma16816(sh, a0, 0u, a2, a3, mine ? vpv[hf] : 0u, mine ? vlo[hf] : 0u);
      mma1688(sh, 0u, c1, mine ? vhi[hf] : 0u);
      if (e == 0 || t >= 2) {
        i0 = r0;
        i1 = r1;
      }
    }
    ov[2 * hf] = pack2(sh[0] * i0, sh[1] * i0);
    ov[2 * hf + 1] = pack2(sh[2] * i1, sh[3] * i1);
  }
  TS(32 + 4 * par + w);
  mbar_wait(sb + OFF_BAR + 8 * B_P1, 0);
  const uint32_t oa = sb + OFF_OA + (lane >> 4) * 2048 + (32 * w + 2 * (lane & 15) + par) * 16;
#pragma unroll
  for (int j = 0; j < 5; j++) stsm4(oa + 4096 * j, ov + 4 * j);
  TSIF(par == 0 && w == 0, 120);
  fence_async_smem();
  TSIF(par == 0 && w == 0, 121);
  __syncwarp();
  if (lane == 0) mbar_arrive(sb + OFF_BAR + 8 * B_ATTN);
  TSM(w == 0 || w == 2, 122 + par + (w == 2 ? 3 : 0));
}

struct Maps {
  CUtensorMap x, wm, wt, k, v, y, wo, qm, qt, om, ot, yl, ol, wh;
};

__device__ __forceinline__ void load_stage(uint32_t sb, int kb, int b, const Maps& m) {
  const uint32_t st = sb + (kb & 3) * STAGE_BYTES, bar = sb + OFF_BAR + 8 * (B_FULL1 + (kb & 3));
  const int r = b >> 3, hg = b & 7, slab = kb - KV_KB;
  const bool kv = slab >= 0 && slab < 5;
  const uint32_t kbar = sb + OFF_BAR + 8 * (B_KV + slab), dst = sb + OFF_KVS + slab * KVS_BYTES;
  mbar_expect_tx(bar, STAGE_BYTES);
  if (kv) mbar_expect_tx(kbar, KVS_BYTES);
  tma_3d(st, &m.x, 64 * kb, 64 * r, 0, bar);
  tma_3d(st + ST_W, &m.wm, 80 * hg + (tail_first(hg) ? 16 : 0), 64 * kb, 0, bar);
  tma_3d(st + ST_WT, &m.wt, 80 * hg + (tail_first(hg) ? 0 : 64), 64 * kb, 0, bar);
  if (kv) tma_3d(dst, &m.k, 0, 32 * (b >> 1) - 3, 2 * slab + (b & 1), kbar);
  if (kv) tma_3d(dst + KVS_V, &m.v, 0, 32 * (b >> 1), 2 * slab + (b & 1), kbar);
}

__global__ void __launch_bounds__(NTHR, 1) fused_kernel(const __grid_constant__ Maps m, const Params p) {
  extern __shared__ __align__(1024) uint8_t smem[];
  const uint32_t sb = (uint32_t)__cvta_generic_to_shared(smem);
  const uint32_t bars = sb + OFF_BAR;
  const int tid = threadIdx.x, lane = tid & 31;
  int b = blockIdx.x;
  b = (((b & 63) >> 3) * 2 + (b & 1)) * 8 + (((b < 64 ? 0x6521 : 0x7430) >> (4 * ((b >> 1) & 3))) & 7);
  const int r = b >> 3, hg = b & 7;

  if (tid == T_ISSUE) {
    TSM(true, 0);
#pragma unroll
    for (int i = 0; i < NS0; i++) mbar_init(bars + 8 * (B_F0 + (i ? 4 + i : 0)), 1);
    fence_async_smem();
#pragma unroll
    for (int i = 0; i < NS0; i++) {
      const uint32_t fb = bars + 8 * (B_F0 + (i ? 4 + i : 0));
      mbar_expect_tx(fb, (i ? 0 : ST_W) + 24576 / NS0);
      if (i == 0 && !W_FIRST) tma_3d(sb, &m.x, 0, 64 * r, 0, fb);
      tma_3d(sb + ST_W + 24576 / NS0 * i, NS0 > 1 ? &m.wh : &m.wm, 80 * hg + (tail_first(hg) ? 16 : 0), 64 / NS0 * i, 0, fb);
      if (i == 0 && W_FIRST) tma_3d(sb, &m.x, 0, 64 * r, 0, fb);
    }
#pragma unroll
    for (int i = 0; i < 4; i++) mbar_init(bars + 8 * (B_FULL1 + i), 1);
    fence_async_smem();
    mbar_expect_tx(bars + 8 * B_FULL1, STAGE_BYTES - ST_WT);
    tma_3d(sb + ST_WT, &m.wt, 80 * hg + (tail_first(hg) ? 0 : 64), 0, 0, bars + 8 * B_FULL1);
    load_stage(sb, 1, b, m);
  } else if (tid == T_INIT) {
#pragma unroll
    for (int i = 0; i < B_F0; i++) mbar_init(bars + 8 * i, i < B_GATE ? 8 : i < B_CVD ? 4 : i == B_CVD ? 20 : 1);
    fence_async_smem();
  }
  const int warp = __shfl_sync(0xffffffffu, tid >> 5, 0), wg = warp >> 2, w = warp & 3;
  __syncthreads();

  if (wg == 3) {
    asm volatile("setmaxnreg.dec.sync.aligned.u32 56;");
    if (w == 0) {
      if (lane == 0) {
#pragma unroll 1
        for (int kb = 2; kb < 10; kb++) {
          if (kb >= 4) mbar_wait(bars + 8 * (kb == 7 ? B_E3 : B_EMPTY1 + (kb & 3)), (kb >> 3) & 1);
          TSIF(kb >= 4, 44 + kb);
          load_stage(sb, kb, b, m);
          TSIF(kb == 3, 60);
          if (kb == 9) mbar_arrive(bars + 8 * B_LAST);
        }
        mbar_wait(bars + 8 * B_WOP, 0);
        mbar_wait(bars + 8 * B_EPOCH, 0);
        flag_wait(g_cnt + C_W + 32 * hg, (lds32(sb + OFF_EPOCH) + 1) * 16);
        TS(30);
#pragma unroll 1
        for (int j = 0; j < 8; j++) {
          if (j >= 6) mbar_wait(bars + 8 * (B_EMPTY2 + j - 6), 0);
          if (j == 4) mbar_wait(bars + 8 * B_ORB, 0);
          TSIF(j >= 6, 100 + j);
          mbar_expect_tx(bars + 8 * (B_FULL2 + j), j == 0 ? WO_BYTES : j == 5 ? O_BYTES + WO_BYTES + 512 : O_BYTES + WO_BYTES);
          bulk_load(sb + off_w(j), g_WO + (hg * 8 + step_src(hg, j)) * 800, WO_BYTES, bars + 8 * (B_FULL2 + j));
        }
        mbar_wait(bars + 8 * (B_EMPTY2 + 3), 0);
        mbar_expect_tx(bars + 8 * B_QF, O_BYTES);
        tma_2d(sb + OFF_QS, &m.qm, 80 * hg, 128 * r, bars + 8 * B_QF);
        tma_2d(sb + OFF_QT, &m.qt, 80 * hg + 64, 128 * r, bars + 8 * B_QF);
      }
    } else if (w == 1) {
      unsigned epoch = 0;
      if (lane == 0) {
        epoch = atomicAdd(g_cnt + C_LAUNCH, 1u) / NCTA;
        asm volatile("st.shared.u32 [%0], %1;" ::"r"(sb + OFF_EPOCH), "r"(epoch) : "memory");
        mbar_arrive(bars + 8 * B_EPOCH);
        mbar_wait(bars + 8 * B_KVD, 0);
        mbar_expect_tx(bars + 8 * B_HB, 5 * 4096);
#pragma unroll 1
        for (int c = 0; c < 5; c++) {
          if (c == 3) mbar_wait(bars + 8 * B_S3, 0);
          bulk_load(sb + off_ch(c) + U_BYTES, p.ssm_k + (5 * b + c) * SEQ, 4096, bars + 8 * B_HB);
        }
#pragma unroll
        for (int c = 0; c < 4; c++) mbar_expect_tx(bars + 8 * (B_U + c), c < 3 ? U_BYTES : 2 * U_BYTES);
        const uint4* usrc = g_U + 5 * b * U_PITCH;
        mbar_wait(bars + 8 * B_USIG, 0);
        flag_wait(g_cnt + C_PREP + 32 * (b & 15), (epoch + 1) * NCTA);
        TS(23);
#pragma unroll
        for (int c = 0; c < 5; c++) {
          if (c == 3) mbar_wait(bars + 8 * (B_U + 2), 0);
          bulk_load(sb + off_ch(c), usrc + c * U_PITCH, U_BYTES, bars + 8 * (B_U + (c < 3 ? c : 3)));
          TSIF(c == 0 || c == 4, 116 + (c >> 2));
        }
      }
      epoch = __shfl_sync(0xffffffffu, epoch, 0);
      if (lane < 8) {
        const int src = (b & ~7) | step_src(hg, lane);
        mbar_wait(bars + 8 * B_ATTN, 0);
        TS(20);
        bool seen = false;
#pragma unroll 1
        for (int spins = 0; spins < SPIN_LIMIT; spins++) {
          const bool now = !seen && (int)(flag_read(g_cnt + C_O + 32 * src) - (epoch + 1)) >= 0;
          if (now && lane >= 1 && lane < 4) bulk_load(sb + off_o(lane), g_O + src * 1280, O_BYTES, bars + 8 * (B_FULL2 + lane));
          seen = seen || now;
          if (__all_sync(0xff, seen)) break;
        }
        TS(21);
        if (lane == 5) bulk_load(sb + OFF_GATE, g_gate + 128 * r, 512, bars + 8 * (B_FULL2 + 5));
#pragma unroll 1
        for (int j = 4; j < 8; j++) {
          if (lane == j) {
            mbar_wait(bars + 8 * (j < 6 ? B_C34 : B_EMPTY2 + j - 6), 0);
            bulk_load(sb + off_o(j), g_O + src * 1280, O_BYTES, bars + 8 * (B_FULL2 + j));
          }
          __syncwarp(0xff);
        }
        TS(22);
      }
    } else if (w == 2) {
      mbar_wait(bars + 8 * B_PREP, 0);
      flag_signal(g_cnt + C_PREP, 16, lane);
      TS(25);
      if (lane == 0) {
        mbar_arrive(bars + 8 * B_USIG);
        mbar_expect_tx(bars + 8 * B_ORB, O_BYTES / 4 + 64);
        mbar_wait(bars + 8 * B_GATE, 0);
        publish(g_gate + 16 * b, sb + OFF_GATE + 64 * hg, 64);
        bulk_load(sb + OFF_GATE + 64 * hg, g_gate + 16 * b, 64, bars + 8 * B_ORB);
        mbar_wait(bars + 8 * B_ATTN, 0);
        publish(g_O + b * 1280, sb + OFF_OA, O_BYTES);
        tma_2d(sb + OFF_KVX + 10240, &m.ol, 48, b * 160, bars + 8 * B_ORB);
        TS(74);
        mbar_wait(bars + 8 * B_ORB, 0);
        flag_bump(g_cnt + C_O + 32 * b);
        TS(26);
      }
    } else {
      if (lane == 0) {
        uint4* dst = g_WO + (hg * 8 + (r >> 1)) * 800 + (r & 1) * 80;
        mbar_wait(bars + 8 * B_S3, 0);
        asm volatile("cp.async.bulk.prefetch.L2.global [%0], 6400;" ::"l"(p.wo + b * 3200) : "memory");
        mbar_wait(bars + 8 * B_P1, 0);
        mbar_wait(bars + 8 * WB_TRIG, 0);
        mbar_expect_tx(bars + 8 * B_WST, WO_BYTES / 2);
        tma_3d(sb + OFF_WA, &m.wo, 0, 40 * r, 5 * hg, bars + 8 * B_WST);
        mbar_wait(bars + 8 * B_WST, 0);
#pragma unroll 1
        for (int n = 0; n < 5; n++) bulk_store(dst + 160 * n, sb + OFF_WA + 1280 * n, 1280);
        bulk_wait_read();
        mbar_expect_tx(bars + 8 * B_WST, WO_BYTES / 2);
#pragma unroll 1
        for (int n = 0; n < 5; n++) bulk_load(sb + OFF_WA + 1280 * n, dst + 160 * n, 1280, bars + 8 * B_WST);
        mbar_wait(bars + 8 * B_WST, 1);
        flag_bump(g_cnt + C_W + 32 * hg);
        mbar_arrive(bars + 8 * B_WOP);
        TS(71);
        mbar_expect_tx(bars + 8 * B_C34, 3 * (U_BYTES / 4));
        mbar_expect_tx(bars + 8 * B_YRB, 2 * (U_BYTES / 4));
#pragma unroll 1
        for (int c = 0; c < 5; c++) {
          mbar_wait(bars + 8 * (B_YST + c), 0);
          publish(g_U + (5 * b + c) * U_PITCH, sb + off_ch(c), U_BYTES);
          tma_2d(sb + off_ch(c), &m.yl, 48, (5 * b + c) * (U_PITCH / 8), bars + 8 * (c < 3 ? B_C34 : B_YRB));
        }
        TS(75);
        mbar_wait(bars + 8 * B_C34, 0);
        mbar_wait(bars + 8 * B_YRB, 0);
        flag_bump(g_cnt + C_Y + 32 * (b >> 4));
        TS(27);
        mbar_expect_tx(bars + 8 * B_YFULL, 20480);
        flag_wait(g_cnt + C_Y + 32 * hg, (lds32(sb + OFF_EPOCH) + 1) * 16);
        TS(24);
        tma_2d(sb + OFF_YT, &m.y, 128 * r, 80 * hg, bars + 8 * B_YFULL);
        tma_2d(sb + OFF_YT + 10240, &m.y, 128 * r + 64, 80 * hg, bars + 8 * B_YFULL);
      }
    }
  } else {
    asm volatile("setmaxnreg.inc.sync.aligned.u32 152;");
    if (wg < 2) {
      float acc[120];
#pragma unroll
      for (int i = 0; i < 120; i++) acc[i] = 0.f;
      const uint32_t da = desc_lo(sb + wg * 8192, 16), db = desc_lo(sb + ST_W, 8192), dc = desc_lo(sb + ST_WT, 2048);
      mbar_wait(bars + 8 * B_F0, 0);
      TSIF(w == 0 && wg == 0, 1);
      wg_fence();
#pragma unroll
      for (int k = 0; k < 4; k++) {
        constexpr int KP = 4 / NS0;
        if (k && k % KP == 0) {
          wg_commit();
          mbar_wait(bars + 8 * (B_F0 + 4 + k / KP), 0);
          wg_fence();
        }
        WgSST<192>::mma<HI_SW128, HI_SW128>(acc, da + 2 * k, desc_lo(sb + ST_W, 8192 / NS0) + 128 * (k % KP) + 1536 / NS0 * (k / KP), 1);
      }
      wg_commit();
      mbar_wait(bars + 8 * B_FULL1, 0);
      wg_fence();
#pragma unroll
      for (int k = 0; k < 4; k++) WgSST<48>::mma<HI_SW128, HI_SW32>(acc + 96, da + 2 * k, dc + 32 * k, 1);
      wg_commit();
#pragma unroll 1
      for (int kb = 1; kb < 10; kb++) {
        mbar_wait(bars + 8 * (B_FULL1 + (kb & 3)), (kb >> 2) & 1);
        const uint32_t so = (kb & 3) * (STAGE_BYTES >> 4);
        wg_fence();
#pragma unroll
        for (int k = 0; k < 4; k++) {
          WgSST<192>::mma<HI_SW128, HI_SW128>(acc, da + so + 2 * k, db + so + 128 * k, 1);
          WgSST<48>::mma<HI_SW128, HI_SW32>(acc + 96, da + so + 2 * k, dc + so + 32 * k, 1);
        }
        wg_commit();
        wg_wait<1>();
        if (lane == 0) mbar_arrive(bars + 8 * (kb == 4 ? B_E3 : B_EMPTY1 + ((kb - 1) & 3)));
      }
      mbar_wait(bars + 8 * B_EPOCH, 0);
      const uint32_t tag = lds32(sb + OFF_EPOCH) + 1;
      mbar_wait(bars + 8 * B_S3, 0);
      wg_wait<0>();
      pin<120>(acc);
      if (lane == 0) mbar_arrive(bars + 8 * B_P1);
      TSM(w == 0, 3 + wg);
      attention(acc, sb, b, wg, w, lane, tag);
    } else {
      const int tw = tid & 127, chl = 64 * (b & 1) + 8 * w + (lane >> 2);
      uint4* up = g_U + chl * U_PITCH + ((4 * (b >> 1) + (lane & 3)) ^ ((b >> 2) & 1));
      uint2 sw[10];
      uint32_t dv = 0;
      if (lane < 5) dv = __ldg(reinterpret_cast<const unsigned short*>(p.ssm_D) + 5 * b + lane);
#pragma unroll
      for (int i = 0; i < 10; i++) sw[i] = ldg64(reinterpret_cast<const uint2*>(p.shift_k) + chl + 128 * (i >> 1) + 32 * (i & 1));
      uint32_t tab[12];
      uint32_t tt[2];
      fft_tables(tab, tw);
      fft_twiddles(tt, tw);
      uint4 res[10];
#pragma unroll
      for (int i = 0; i < 10; i++) res[i] = make_uint4(0, 0, 0, 0);
#pragma unroll 1
      for (int slab = 0; slab < 5; slab++) {
#pragma unroll
        for (int i = 0; i < 8; i++) res[i] = res[i + 2];
        prep_slab(res + 8, sw, sb, slab, w, lane);
        TSIF(w == 0, 99 + 4 * slab);
#pragma unroll
        for (int i = 0; i < 8; i++) sw[i] = sw[i + 2];
      }
      TSIF(w == 0, 28);
      __syncwarp();
      if (lane == 0) mbar_arrive(bars + 8 * B_KVD + ((res[8].x ^ res[9].x) & p.zero));
      mbar_wait(bars + 8 * B_KVD, 0);
      fft_tables_store(tab, sb, tw);
      mbar_wait(bars + 8 * B_LAST, 0);
#pragma unroll
      for (int i = 0; i < 10; i++) up[(128 * (i >> 1) + 32 * (i & 1)) * U_PITCH] = res[i];
      __syncwarp();
      if (lane == 0) mbar_arrive(bars + 8 * B_PREP);
      TSIF(w == 0, 5);
      mbar_wait(bars + 8 * B_LAST, 0);
      prep_gate(p, sb, b, w, lane);
      __syncwarp();
      if (lane == 0) mbar_arrive(bars + 8 * B_GATE);
      TSIF(w == 0, 72);
      mbar_wait(bars + 8 * B_HB, 0);
      TSIF(w == 0, 2);
      const uint32_t ha = sb + U_BYTES + ((tw >> 3) * 16 + 8 + (tw & 7)) * 16;
      uint4 hv[5];
#pragma unroll
      for (int c = 0; c < 5; c++) hv[c] = lds128(ha + off_ch(c));
      __syncwarp();
#pragma unroll
      for (int c = 0; c < 5; c++) sts128((ha ^ 16) + off_ch(c), hv[c].x, hv[c].y, hv[c].z, hv[c].w);
      asm volatile("st.shared.v2.u32 [%0], {%1, %2};" ::"r"(sb + OFF_TT + 8 * tw), "r"(tt[0]), "r"(tt[1]) : "memory");
      if (tw < 5) asm volatile("st.shared.f32 [%0], %1;" ::"r"(sb + OFF_D + 4 * tw), "f"(bf_lo(dv) * 0.125f) : "memory");
      fence_async_smem();
      __syncwarp();
      if (lane == 0) mbar_arrive(bars + 8 * B_HA);
      TSIF(w == 0, 6);
    }

    FftConst fc;
    TSM(w == 0 && wg == 0, 104);
    mbar_wait(bars + 8 * B_HA, 0);
    fft_matrices(fc, sb, w, lane);
    TSM(w == 0 && wg == 0, 105);
    TSM(w == 0 && wg == 2, 124);
#pragma unroll 1
    for (uint32_t tasks = wg == 0 ? TASK0 : wg == 1 ? TASK1 : TASK2; tasks; tasks >>= 4) {
      const int c = (tasks & 7) - 1;
      conv_channel(fc, sb, c, wg, w, lane);
      if (lane == 0) mbar_arrive(bars + 8 * (B_YST + c));
      TSM(w == 0, 10 + c);
    }

    if (wg != 1) {
      const int wg = warp >> 3;
      const int g = lane >> 2;
      float acc[40];
#pragma unroll
      for (int i = 0; i < 40; i++) acc[i] = 0.f;
      const uint32_t da = desc_lo(sb + wg * 1024, 2048), db = desc_lo(sb, 2560);
      mbar_wait(bars + 8 * B_ORB, 0);
      mbar_wait(bars + 8 * B_FULL2, 0);
      TSM(w == 0, 15 + wg);
#pragma unroll 1
      for (int j = 0; j < 8; j++) {
        if (j == 1 - wg) mbar_wait(bars + 8 * B_CVD, 0);
        mbar_wait(bars + 8 * (B_FULL2 + j), 0);
        TSM(w == 0 && wg == 0, 44 + (j < 4 ? j : j + 6));
        const uint32_t oa = da + (off_o(j) >> 4), ob = db + (off_w(j) >> 4);
        wg_fence();
#pragma unroll
        for (int k = 0; k < 5; k++) WgSST<80>::mma<HI_NONE, HI_SW32>(acc, oa + 256 * k, ob + 32 * k, 1);
        wg_commit();
        wg_wait<1>();
        if (j >= 1 && j <= 4 && lane == 0) mbar_arrive(bars + 8 * (B_EMPTY2 + j - 1));
      }
      TSIF(w == 0 && wg == 0, 113);
      const int tr = 64 * wg + 16 * w + (lane & 15);
      const uint32_t fm = sb + OFF_QS + tr * 128, fx = (lane >> 4) ^ (tr & 7);
      const uint32_t ft = sb + OFF_QT + tr * 32 + (((lane >> 4) ^ (tr >> 2)) & 1) * 16;
      const float g0 = __uint_as_float(lds32(sb + OFF_GATE + (64 * wg + 16 * w + g) * 4));
      const float g1 = __uint_as_float(lds32(sb + OFF_GATE + (64 * wg + 16 * w + 8 + g) * 4));
      const uint32_t ga = pack2(g0, g0), gb = pack2(g1, g1);
      const uint32_t na = pack2(1.f - g0, 1.f - g0), nb = pack2(1.f - g1, 1.f - g1);

      uint32_t qf[20];
      mbar_wait(bars + 8 * B_QF, 0);
      TSM(w == 0 && wg == 0, 99);
#pragma unroll
      for (int j = 0; j < 5; j++) ldsm4(qf + 4 * j, j < 4 ? fm + ((fx ^ (2 * j)) << 4) : ft);
#pragma unroll
      for (int i = 0; i < 20; i++) {
        qf[i] = bmul((i & 1) ? gb : ga, qf[i]);
        asm volatile("" : "+r"(qf[i]));
      }

      wg_wait<0>();
      pin<40>(acc);
      TSM(w == 0, 17 + wg);
      uint32_t pb[20];
#pragma unroll
      for (int j = 0; j < 10; j++) {
        pb[2 * j] = bmul(na, pack2(acc[4 * j], acc[4 * j + 1]));
        pb[2 * j + 1] = bmul(nb, pack2(acc[4 * j + 2], acc[4 * j + 3]));
        asm volatile("" : "+r"(pb[2 * j]), "+r"(pb[2 * j + 1]));
      }
      const uint32_t ya = sb + OFF_YT + wg * 10240 + ((lane >> 4) * 8 + (lane & 7)) * 128 +
                          (((2 * w + (((lane >> 3) & 1) ^ wg)) ^ (lane & 7)) << 4);
      mbar_wait(bars + 8 * B_YFULL, 0);
      TSM(w == 0 && wg == 0, 19);
#pragma unroll
      for (int j = 0; j < 5; j++) {
        uint32_t y[4];
        ldsm4t(y, ya + 2048 * j);
#pragma unroll
        for (int i = 0; i < 4; i++)
          qf[4 * j + i] = bfma(qf[4 * j + i], y[i], pb[4 * j + i]);
      }
#pragma unroll
      for (int j = 0; j < 5; j++) stsm4(j < 4 ? fm + ((fx ^ (2 * j)) << 4) : ft, qf + 4 * j);
      fence_async_smem();
      __syncwarp();
      if (lane == 0) {
        const int row = 64 * wg + 16 * w;
        asm volatile("cp.async.bulk.tensor.2d.global.shared::cta.bulk_group [%0, {%2, %3}], [%1];"
                     ::"l"(&m.om), "r"(sb + OFF_QS + row * 128), "r"(80 * hg), "r"(128 * r + row) : "memory");
        asm volatile("cp.async.bulk.tensor.2d.global.shared::cta.bulk_group [%0, {%2, %3}], [%1];"
                     ::"l"(&m.ot), "r"(sb + OFF_QT + row * 32), "r"(80 * hg + 64), "r"(128 * r + row) : "memory");
        asm volatile("cp.async.bulk.commit_group;\ncp.async.bulk.wait_group.read 0;" ::: "memory");
      }
      TSM(w == 0 || w == 3, 40 + 2 * wg + (w & 1));
    }
  }
}

typedef CUresult (*EncodeFn)(CUtensorMap*, CUtensorMapDataType, cuuint32_t, void*, const cuuint64_t*, const cuuint64_t*,
                             const cuuint32_t*, const cuuint32_t*, CUtensorMapInterleave, CUtensorMapSwizzle,
                             CUtensorMapL2promotion, CUtensorMapFloatOOBfill);

void encode(EncodeFn fn, CUtensorMap* tm, const void* base, int rank, const cuuint64_t* dims, const cuuint64_t* strides,
            const cuuint32_t* box, CUtensorMapSwizzle swz) {
  const cuuint32_t ones[3] = {1, 1, 1};
  fn(tm, CU_TENSOR_MAP_DATA_TYPE_BFLOAT16, rank, const_cast<void*>(base), dims, strides, box, ones,
     CU_TENSOR_MAP_INTERLEAVE_NONE, swz, CU_TENSOR_MAP_L2_PROMOTION_L2_128B, CU_TENSOR_MAP_FLOAT_OOB_FILL_NONE);
}

}

extern "C" void kernel_launch(void* const* d_in, const int* in_sizes, int n_in, void* d_out, int out_size) {
  (void)in_sizes; (void)n_in; (void)out_size;
  Params p;
  p.q = (const __nv_bfloat16*)d_in[0];
  p.k = (const __nv_bfloat16*)d_in[1];
  p.v = (const __nv_bfloat16*)d_in[2];
  p.shift_k = (const __nv_bfloat16*)d_in[3];
  p.ssm_k = (const __nv_bfloat16*)d_in[4];
  p.ssm_D = (const __nv_bfloat16*)d_in[5];
  p.wqkv = (const __nv_bfloat16*)d_in[7];
  p.wo = (const __nv_bfloat16*)d_in[8];
  p.gate_w = (const __nv_bfloat16*)d_in[9];
  p.out = (__nv_bfloat16*)d_out;
  p.zero = 0;

  static EncodeFn fn = nullptr;
  static void *yaddr = nullptr, *oaddr = nullptr;
  if (!fn) {
    cudaDriverEntryPointQueryResult qr;
    void* f = nullptr;
    cudaGetDriverEntryPoint("cuTensorMapEncodeTiled", &f, cudaEnableDefault, &qr);
    fn = (EncodeFn)f;
    cudaGetSymbolAddress(&yaddr, g_U);
    cudaGetSymbolAddress(&oaddr, g_O);
    cudaFuncSetAttribute(fused_kernel, cudaFuncAttributeMaxDynamicSharedMemorySize, SMEM_BYTES);
  }
  Maps m;
  {
    const cuuint64_t dims[3] = {640, 1024, 2}, st[2] = {2560, 1280};
    const cuuint32_t box[3] = {64, 64, 2};
    encode(fn, &m.x, p.q, 3, dims, st, box, CU_TENSOR_MAP_SWIZZLE_128B);
  }
  {
    const cuuint64_t dims[3] = {640, 640, 3}, st[2] = {3840, 1280};
    const cuuint32_t box[3] = {64, 64, 3}, boxt[3] = {16, 64, 3};
    encode(fn, &m.wm, p.wqkv, 3, dims, st, box, CU_TENSOR_MAP_SWIZZLE_128B);
    encode(fn, &m.wt, p.wqkv, 3, dims, st, boxt, CU_TENSOR_MAP_SWIZZLE_32B);
    const cuuint32_t boxh[3] = {64, 64 / NS0, 3};
    encode(fn, &m.wh, p.wqkv, 3, dims, st, boxh, CU_TENSOR_MAP_SWIZZLE_128B);
  }
  {
    const cuuint64_t dims[3] = {64, 2048, 10}, st[2] = {1280, 128};
    const cuuint32_t boxk[3] = {64, 35, 1}, boxv[3] = {64, 32, 1};
    encode(fn, &m.k, p.k, 3, dims, st, boxk, CU_TENSOR_MAP_SWIZZLE_128B);
    encode(fn, &m.v, p.v, 3, dims, st, boxv, CU_TENSOR_MAP_SWIZZLE_128B);
  }
  {
    const cuuint64_t dims[3] = {16, 640, 40}, st[2] = {1280, 32};
    const cuuint32_t box[3] = {16, 40, 5};
    encode(fn, &m.wo, p.wo, 3, dims, st, box, CU_TENSOR_MAP_SWIZZLE_32B);
  }
  {
    const cuuint64_t dims[2] = {2048, 640}, st[1] = {U_PITCH * 16};
    const cuuint32_t box[2] = {64, 80};
    encode(fn, &m.y, yaddr, 2, dims, st, box, CU_TENSOR_MAP_SWIZZLE_128B);
    const cuuint64_t dl[2] = {64, DIM * U_PITCH / 8}, dol[2] = {64, NCTA * 160}, sl[1] = {128};
    const cuuint32_t bl[2] = {16, 32}, bol[2] = {16, 160};
    encode(fn, &m.yl, yaddr, 2, dl, sl, bl, CU_TENSOR_MAP_SWIZZLE_NONE);
    encode(fn, &m.ol, oaddr, 2, dol, sl, bol, CU_TENSOR_MAP_SWIZZLE_NONE);
  }
  {
    const cuuint64_t dims[2] = {640, 2048}, st[1] = {1280};
    const cuuint32_t bqm[2] = {64, 128}, bqt[2] = {16, 128}, bom[2] = {64, 16}, bot[2] = {16, 16};
    encode(fn, &m.qm, p.q, 2, dims, st, bqm, CU_TENSOR_MAP_SWIZZLE_128B);
    encode(fn, &m.qt, p.q, 2, dims, st, bqt, CU_TENSOR_MAP_SWIZZLE_32B);
    encode(fn, &m.om, p.out, 2, dims, st, bom, CU_TENSOR_MAP_SWIZZLE_128B);
    encode(fn, &m.ot, p.out, 2, dims, st, bot, CU_TENSOR_MAP_SWIZZLE_32B);
  }
  fused_kernel<<<NCTA, NTHR, SMEM_BYTES>>>(m, p);
}
```

```cpp
#include <cuda.h>
#include <cuda_bf16.h>
#include <cuda_runtime.h>
#include <stdint.h>

namespace {

constexpr int SEQ = 2048, DIM = 640, NCTA = 128, NTHR = 512;

#define KV_KB 2
#define DEV_EXIT 0
#define FENCE_LO 0
#define FENCE_HI 0
#define WB_TRIG B_USIG
#define T_ISSUE 288
#define NS0 4
#define W_FIRST 0
#define SPLIT1 1
#define T_INIT 448
#define TASK0 0x3
#define TASK1 0x52
#define TASK2 0x41

constexpr uint32_t STAGE_BYTES = 47104, ST_W = 16384, ST_WT = 40960;
constexpr uint32_t O_BYTES = 20480, WO_BYTES = 12800;
constexpr uint32_t OFF_OA = 0;
constexpr uint32_t OFF_QS = 3 * O_BYTES, OFF_QT = OFF_QS + 16384;
constexpr uint32_t OFF_WC = 81920;
constexpr uint32_t OFF_WA = 94720;
constexpr uint32_t OFF_GATE = 145920;
constexpr uint32_t OFF_TT = 146432;
constexpr uint32_t OFF_KVX = 148480;
constexpr uint32_t OFF_CH3 = 163840;
constexpr uint32_t CH_BYTES = 12288, U_BYTES = 4096;
constexpr uint32_t OFF_FT = 225280, OFF_GT = 229376;
constexpr uint32_t OFF_CH0 = 188416;
constexpr uint32_t OFF_KVS = OFF_CH0, KVS_V = 4480, KVS_BYTES = 8576;
constexpr uint32_t OFF_YT = 163840;
constexpr uint32_t OFF_BAR = 231936;
constexpr uint32_t SMEM_BYTES = OFF_BAR + 512;

enum : uint32_t {
  B_EMPTY1 = 0, B_S3 = 3, B_E3 = 4, B_EMPTY2 = 5, B_ATTN = 9, B_P1 = 10,
  B_GATE = 11, B_HA = 12, B_KVD = 13, B_PREP = 14, B_YST = 15,
  B_CVD = 20,
  B_FULL2 = 21, B_U = 29, B_KV = 33, B_HB = 38, B_C34 = 39, B_YRB = 40, B_YFULL = 41, B_EPOCH = 42, B_LAST = 43,
  B_WOP = 44, B_USIG = 45, B_WST = 46, B_QF = 47, B_ORB = 48,
  B_F0 = 49, B_FULL1 = 50, B_F1 = 57
};
constexpr uint32_t OFF_EPOCH = OFF_BAR + 8 * 58, OFF_D = OFF_BAR + 8 * 60;
__device__ __forceinline__ uint32_t off_o(int j) { return j < 4 ? OFF_OA + j * O_BYTES : j < 6 ? OFF_CH0 + (j - 4) * O_BYTES : OFF_OA + (j - 6) * O_BYTES; }
__device__ __forceinline__ uint32_t off_w(int j) { return j < 4 ? OFF_WA + j * WO_BYTES : j == 4 ? OFF_KVX : j == 5 ? OFF_WC : OFF_WA + (j - 6) * WO_BYTES; }
__device__ __forceinline__ int step_src(int hg, int j) { return j == 0 ? hg : j <= hg ? j - 1 : j; }
__device__ __forceinline__ bool tail_first(int hg) { return (hg & 3) == 3; }
__device__ __forceinline__ uint32_t off_ch(int c) { return (c < 3 ? OFF_CH0 : OFF_CH3 - 3 * CH_BYTES) + c * CH_BYTES; }

#define U_PITCH 264
__device__ __align__(1024) uint4 g_U[DIM * U_PITCH];
__device__ __align__(128) uint4 g_O[NCTA * 1280];
__device__ uint4 g_WO[64 * 800];
__device__ uint4 g_halo[NCTA * 2 * 7 * 32];
__device__ __align__(128) float g_gate[SEQ];
__device__ unsigned g_cnt[32 * (1 + 2 * 16 + 8 + NCTA)];
constexpr int C_LAUNCH = 0, C_PREP = 32, C_Y = 32 * 17, C_W = 32 * 33, C_O = 32 * 41;

#define TSM(cond, slot) do { } while (0)
#define TSIF(cond, slot) do { if (__LINE__ >= FENCE_LO && __LINE__ < FENCE_HI) sched_fence(); } while (0)
__device__ __forceinline__ void sched_fence() {
  asm volatile("{\n.reg .pred p;\n.reg .u32 c;\nmov.u32 c, %%clock;\nsetp.eq.u32 p, c, 0;\n@p st.shared.u32 [%0], c;\n}"
               ::"r"(1024 + OFF_EPOCH + 4) : "memory");
}
#define TS(slot) TSIF(true, slot)

struct Params {
  const __nv_bfloat16 *q, *k, *v, *shift_k, *ssm_k, *ssm_D, *wqkv, *wo, *gate_w;
  __nv_bfloat16* out;
  uint32_t zero;
};

constexpr int SPIN_LIMIT = 1 << 17;

__device__ __forceinline__ void mbar_init(uint32_t bar, uint32_t count) {
  asm volatile("mbarrier.init.shared::cta.b64 [%0], %1;" ::"r"(bar), "r"(count) : "memory");
}
__device__ __forceinline__ void mbar_expect_tx(uint32_t bar, uint32_t bytes) {
  asm volatile("mbarrier.arrive.expect_tx.shared::cta.b64 _, [%0], %1;" ::"r"(bar), "r"(bytes) : "memory");
}
__device__ __forceinline__ void mbar_arrive(uint32_t bar) {
  asm volatile("mbarrier.arrive.shared::cta.b64 _, [%0];" ::"r"(bar) : "memory");
}
__device__ __forceinline__ void mbar_wait(uint32_t bar, uint32_t parity) {
  uint32_t ok;
  int spins = 0;
  do {
      asm volatile("{\n.reg .pred p;\nmbarrier.try_wait.parity.shared::cta.b64 p, [%1], %2;\nselp.b32 %0, 1, 0, p;\n}"
                   : "=r"(ok) : "r"(bar), "r"(parity) : "memory");
    if (++spins > SPIN_LIMIT) break;
  } while (!ok);
}
__device__ __forceinline__ unsigned flag_read(const unsigned* p) {
  unsigned v;
  asm volatile("ld.relaxed.gpu.global.u32 %0, [%1];" : "=r"(v) : "l"(p) : "memory");
  return v;
}
__device__ __forceinline__ void flag_poll(const unsigned* p, unsigned target) {
  unsigned v;
  int spins = 0;
  do {
    asm volatile("ld.relaxed.gpu.global.u32 %0, [%1];" : "=r"(v) : "l"(p) : "memory");
    if (++spins > SPIN_LIMIT) break;
  } while ((int)(v - target) < 0);
}
__device__ __forceinline__ void flag_wait(const unsigned* p, unsigned target) {
  flag_poll(p, target);
}
__device__ __forceinline__ void flag_signal(unsigned* p, int n, int lane) {
  if (lane == 0) asm volatile("fence.release.gpu;" ::: "memory");
  __syncwarp();
  if (lane < n) asm volatile("red.relaxed.gpu.global.add.u32 [%0], 1;" ::"l"(p + 32 * lane) : "memory");
}
__device__ __forceinline__ void flag_bump(unsigned* p) {
  asm volatile("red.relaxed.gpu.global.add.u32 [%0], 1;" ::"l"(p) : "memory");
}
__device__ __forceinline__ void fence_async_smem() { asm volatile("fence.proxy.async.shared::cta;" ::: "memory"); }
__device__ __forceinline__ void wg_sync(int id) { asm volatile("bar.sync %0, 128;" ::"r"(id) : "memory"); }

__device__ __forceinline__ void tma_2d(uint32_t dst, const CUtensorMap* tm, int c0, int c1, uint32_t bar) {
  asm volatile("cp.async.bulk.tensor.2d.shared::cluster.global.mbarrier::complete_tx::bytes [%0], [%1, {%3, %4}], [%2];"
               ::"r"(dst), "l"(tm), "r"(bar), "r"(c0), "r"(c1) : "memory");
}
__device__ __forceinline__ void tma_3d(uint32_t dst, const CUtensorMap* tm, int c0, int c1, int c2, uint32_t bar) {
  asm volatile("cp.async.bulk.tensor.3d.shared::cluster.global.mbarrier::complete_tx::bytes [%0], [%1, {%3, %4, %5}], [%2];"
               ::"r"(dst), "l"(tm), "r"(bar), "r"(c0), "r"(c1), "r"(c2) : "memory");
}
__device__ __forceinline__ void bulk_load(uint32_t dst, const void* src, uint32_t bytes, uint32_t bar) {
  asm volatile("cp.async.bulk.shared::cluster.global.mbarrier::complete_tx::bytes [%0], [%1], %2, [%3];"
               ::"r"(dst), "l"(src), "r"(bytes), "r"(bar) : "memory");
}
__device__ __forceinline__ void bulk_store(void* dst, uint32_t src, uint32_t bytes) {
  asm volatile("cp.async.bulk.global.shared::cta.bulk_group [%0], [%1], %2;" ::"l"(dst), "r"(src), "r"(bytes) : "memory");
}
__device__ __forceinline__ void bulk_wait_read() {
  asm volatile("cp.async.bulk.commit_group;\ncp.async.bulk.wait_group.read 0;" ::: "memory");
}

__device__ __forceinline__ void publish(void* dst, uint32_t src, uint32_t bytes) {
  bulk_store(dst, src, bytes);
  bulk_wait_read();
}

__device__ __forceinline__ void wg_fence() { asm volatile("wgmma.fence.sync.aligned;" ::: "memory"); }
__device__ __forceinline__ void wg_commit() { asm volatile("wgmma.commit_group.sync.aligned;" ::: "memory"); }
template <int N> __device__ __forceinline__ void wg_wait() { asm volatile("wgmma.wait_group.sync.aligned %0;" ::"n"(N) : "memory"); }
__device__ __forceinline__ uint32_t desc_lo(uint32_t addr, uint32_t lbo) { return ((addr & 0x3FFFF) >> 4) | ((lbo >> 4) << 16); }
constexpr uint32_t desc_hi(uint32_t sbo, uint32_t swz) { return (sbo >> 4) | (swz << 30); }
constexpr uint32_t HI_SW128 = desc_hi(1024, 1), HI_SW64 = desc_hi(512, 2), HI_SW32 = desc_hi(256, 3), HI_NONE = desc_hi(128, 0);
template <int N> __device__ __forceinline__ void pin(float* d) {
#pragma unroll
  for (int i = 0; i < N; i++) asm volatile("" : "+f"(d[i])::"memory");
}

__device__ __forceinline__ uint32_t lds32(uint32_t a) {
  uint32_t v;
  asm volatile("ld.volatile.shared.u32 %0, [%1];" : "=r"(v) : "r"(a) : "memory");
  return v;
}
__device__ __forceinline__ uint2 ldg64(const void* a) {
  uint2 v;
  asm volatile("ld.global.nc.v2.u32 {%0, %1}, [%2];" : "=r"(v.x), "=r"(v.y) : "l"(a) : "memory");
  return v;
}
__device__ __forceinline__ void ldsm4(uint32_t* r, uint32_t a) {
  asm volatile("ldmatrix.sync.aligned.m8n8.x4.shared.b16 {%0, %1, %2, %3}, [%4];"
               : "=r"(r[0]), "=r"(r[1]), "=r"(r[2]), "=r"(r[3]) : "r"(a) : "memory");
}
__device__ __forceinline__ void ldsm4t(uint32_t* r, uint32_t a) {
  asm volatile("ldmatrix.sync.aligned.m8n8.x4.trans.shared.b16 {%0, %1, %2, %3}, [%4];"
               : "=r"(r[0]), "=r"(r[1]), "=r"(r[2]), "=r"(r[3]) : "r"(a) : "memory");
}
__device__ __forceinline__ uint2 lds64(uint32_t a) {
  uint2 v;
  asm volatile("ld.shared.v2.u32 {%0, %1}, [%2];" : "=r"(v.x), "=r"(v.y) : "r"(a) : "memory");
  return v;
}
__device__ __forceinline__ uint4 lds128(uint32_t a) {
  uint4 v;
  asm volatile("ld.shared.v4.u32 {%0, %1, %2, %3}, [%4];" : "=r"(v.x), "=r"(v.y), "=r"(v.z), "=r"(v.w) : "r"(a) : "memory");
  return v;
}
__device__ __forceinline__ void sts128(uint32_t a, uint32_t x, uint32_t y, uint32_t z, uint32_t w) {
  asm volatile("st.shared.v4.u32 [%0], {%1, %2, %3, %4};" ::"r"(a), "r"(x), "r"(y), "r"(z), "r"(w) : "memory");
}
__device__ __forceinline__ void stsm4(uint32_t a, const uint32_t* r) {
  asm volatile("stmatrix.sync.aligned.m8n8.x4.shared.b16 [%0], {%1, %2, %3, %4};" ::"r"(a), "r"(r[0]), "r"(r[1]), "r"(r[2]), "r"(r[3]) : "memory");
}
__device__ __forceinline__ uint32_t pack2(float lo, float hi) {
  uint32_t r;
  asm("cvt.rn.bf16x2.f32 %0, %1, %2;" : "=r"(r) : "f"(hi), "f"(lo));
  return r;
}
__device__ __forceinline__ uint32_t movm(uint32_t a) {
  uint32_t d;
  asm volatile("movmatrix.sync.aligned.m8n8.trans.b16 %0, %1;" : "=r"(d) : "r"(a));
  return d;
}
__device__ __forceinline__ uint32_t bmul(uint32_t a, uint32_t b) {
  uint32_t d;
  asm("mul.rn.bf16x2 %0, %1, %2;" : "=r"(d) : "r"(a), "r"(b));
  return d;
}
__device__ __forceinline__ uint32_t badd(uint32_t a, uint32_t b) {
  uint32_t d;
  asm("add.rn.bf16x2 %0, %1, %2;" : "=r"(d) : "r"(a), "r"(b));
  return d;
}
__device__ __forceinline__ uint32_t bfma(uint32_t a, uint32_t b, uint32_t c) {
  uint32_t d;
  asm("fma.rn.bf16x2 %0, %1, %2, %3;" : "=r"(d) : "r"(a), "r"(b), "r"(c));
  return d;
}
__device__ __forceinline__ float bf_lo(uint32_t x) { return __uint_as_float(x << 16); }
__device__ __forceinline__ float bf_hi(uint32_t x) { return __uint_as_float(x & 0xFFFF0000u); }
__device__ __forceinline__ float ex2(float x) {
  float y;
  asm("ex2.approx.ftz.f32 %0, %1;" : "=f"(y) : "f"(x));
  return y;
}
__device__ __forceinline__ float rcp(float x) {
  float y;
  asm("rcp.approx.ftz.f32 %0, %1;" : "=f"(y) : "f"(x));
  return y;
}
__device__ __forceinline__ void mma16816(float* d, uint32_t a0, uint32_t a1, uint32_t a2, uint32_t a3, uint32_t b0, uint32_t b1) {
  asm volatile("mma.sync.aligned.m16n8k16.row.col.f32.bf16.bf16.f32 {%0, %1, %2, %3}, {%4, %5, %6, %7}, {%8, %9}, {%0, %1, %2, %3};"
               : "+f"(d[0]), "+f"(d[1]), "+f"(d[2]), "+f"(d[3])
               : "r"(a0), "r"(a1), "r"(a2), "r"(a3), "r"(b0), "r"(b1));
}
__device__ __forceinline__ void mma1688(float* d, uint32_t a0, uint32_t a1, uint32_t b0) {
  asm volatile("mma.sync.aligned.m16n8k8.row.col.f32.bf16.bf16.f32 {%0, %1, %2, %3}, {%4, %5}, {%6}, {%0, %1, %2, %3};"
               : "+f"(d[0]), "+f"(d[1]), "+f"(d[2]), "+f"(d[3])
               : "r"(a0), "r"(a1), "r"(b0));
}

template <int N> struct WgRS;
template <int N> struct WgSST;
template <> struct WgRS<32> {
  template <uint32_t HB>
  static __device__ __forceinline__ void mma(float* d, const uint32_t* a, uint32_t db) {
    asm volatile("{\n.reg .pred p;\n.reg .b64 db;\nsetp.ne.b32 p, %22, 0;\n"
      "mov.b64 db, {%20, %21};\n"
      "wgmma.mma_async.sync.aligned.m64n32k16.f32.bf16.bf16 {"
      "%0, %1, %2, %3, %4, %5, %6, %7, %8, %9, %10, %11, %12, %13, %14, %15"
      "}, {%16, %17, %18, %19}, db, p, 1, 1, 1;\n}\n"
      : "+f"(d[0]), "+f"(d[1]), "+f"(d[2]), "+f"(d[3]), "+f"(d[4]), "+f"(d[5]), "+f"(d[6]), "+f"(d[7]),
        "+f"(d[8]), "+f"(d[9]), "+f"(d[10]), "+f"(d[11]), "+f"(d[12]), "+f"(d[13]), "+f"(d[14]), "+f"(d[15])
      : "r"(a[0]), "r"(a[1]), "r"(a[2]), "r"(a[3]), "r"(db), "n"(HB), "n"(1));
  }
  template <uint32_t HB>
  static __device__ __forceinline__ void set(float* d, const uint32_t* a, uint32_t db) {
    asm volatile("{\n.reg .pred p;\n.reg .b64 db;\nsetp.ne.b32 p, %22, 0;\n"
      "mov.b64 db, {%20, %21};\n"
      "wgmma.mma_async.sync.aligned.m64n32k16.f32.bf16.bf16 {"
      "%0, %1, %2, %3, %4, %5, %6, %7, %8, %9, %10, %11, %12, %13, %14, %15"
      "}, {%16, %17, %18, %19}, db, p, 1, 1, 1;\n}\n"
      : "=f"(d[0]), "=f"(d[1]), "=f"(d[2]), "=f"(d[3]), "=f"(d[4]), "=f"(d[5]), "=f"(d[6]), "=f"(d[7]),
        "=f"(d[8]), "=f"(d[9]), "=f"(d[10]), "=f"(d[11]), "=f"(d[12]), "=f"(d[13]), "=f"(d[14]), "=f"(d[15])
      : "r"(a[0]), "r"(a[1]), "r"(a[2]), "r"(a[3]), "r"(db), "n"(HB), "n"(0));
  }
};
template <> struct WgRS<64> {
  template <uint32_t HB>
  static __device__ __forceinline__ void mma(float* d, const uint32_t* a, uint32_t db) {
    asm volatile("{\n.reg .pred p;\n.reg .b64 db;\nsetp.ne.b32 p, %38, 0;\n"
      "mov.b64 db, {%36, %37};\n"
      "wgmma.mma_async.sync.aligned.m64n64k16.f32.bf16.bf16 {"
      "%0, %1, %2, %3, %4, %5, %6, %7, %8, %9, %10, %11, %12, %13, %14, %15, "
      "%16, %17, %18, %19, %20, %21, %22, %23, %24, %25, %26, %27, %28, %29, %30, %31"
      "}, {%32, %33, %34, %35}, db, p, 1, 1, 1;\n}\n"
      : "+f"(d[0]), "+f"(d[1]), "+f"(d[2]), "+f"(d[3]), "+f"(d[4]), "+f"(d[5]), "+f"(d[6]), "+f"(d[7]),
        "+f"(d[8]), "+f"(d[9]), "+f"(d[10]), "+f"(d[11]), "+f"(d[12]), "+f"(d[13]), "+f"(d[14]), "+f"(d[15]),
        "+f"(d[16]), "+f"(d[17]), "+f"(d[18]), "+f"(d[19]), "+f"(d[20]), "+f"(d[21]), "+f"(d[22]), "+f"(d[23]),
        "+f"(d[24]), "+f"(d[25]), "+f"(d[26]), "+f"(d[27]), "+f"(d[28]), "+f"(d[29]), "+f"(d[30]), "+f"(d[31])
      : "r"(a[0]), "r"(a[1]), "r"(a[2]), "r"(a[3]), "r"(db), "n"(HB), "n"(1));
  }
  template <uint32_t HB>
  static __device__ __forceinline__ void set(float* d, const uint32_t* a, uint32_t db) {
    asm volatile("{\n.reg .pred p;\n.reg .b64 db;\nsetp.ne.b32 p, %38, 0;\n"
      "mov.b64 db, {%36, %37};\n"
      "wgmma.mma_async.sync.aligned.m64n64k16.f32.bf16.bf16 {"
      "%0, %1, %2, %3, %4, %5, %6, %7, %8, %9, %10, %11, %12, %13, %14, %15, "
      "%16, %17, %18, %19, %20, %21, %22, %23, %24, %25, %26, %27, %28, %29, %30, %31"
      "}, {%32, %33, %34, %35}, db, p, 1, 1, 1;\n}\n"
      : "=f"(d[0]), "=f"(d[1]), "=f"(d[2]), "=f"(d[3]), "=f"(d[4]), "=f"(d[5]), "=f"(d[6]), "=f"(d[7]),
        "=f"(d[8]), "=f"(d[9]), "=f"(d[10]), "=f"(d[11]), "=f"(d[12]), "=f"(d[13]), "=f"(d[14]), "=f"(d[15]),
        "=f"(d[16]), "=f"(d[17]), "=f"(d[18]), "=f"(d[19]), "=f"(d[20]), "=f"(d[21]), "=f"(d[22]), "=f"(d[23]),
        "=f"(d[24]), "=f"(d[25]), "=f"(d[26]), "=f"(d[27]), "=f"(d[28]), "=f"(d[29]), "=f"(d[30]), "=f"(d[31])
      : "r"(a[0]), "r"(a[1]), "r"(a[2]), "r"(a[3]), "r"(db), "n"(HB), "n"(0));
  }
};
template <> struct WgSST<48> {
  template <uint32_t HA, uint32_t HB>
  static __device__ __forceinline__ void mma(float* d, uint32_t da, uint32_t db, int sc) {
    asm volatile("{\n.reg .pred p;\n.reg .b64 da, db;\nsetp.ne.b32 p, %28, 0;\n"
      "mov.b64 da, {%24, %25};\nmov.b64 db, {%26, %27};\n"
      "wgmma.mma_async.sync.aligned.m64n48k16.f32.bf16.bf16 {"
      "%0, %1, %2, %3, %4, %5, %6, %7, %8, %9, %10, %11, %12, %13, %14, %15, "
      "%16, %17, %18, %19, %20, %21, %22, %23"
      "}, da, db, p, 1, 1, 0, 1;\n}\n"
      : "+f"(d[0]), "+f"(d[1]), "+f"(d[2]), "+f"(d[3]), "+f"(d[4]), "+f"(d[5]), "+f"(d[6]), "+f"(d[7]),
        "+f"(d[8]), "+f"(d[9]), "+f"(d[10]), "+f"(d[11]), "+f"(d[12]), "+f"(d[13]), "+f"(d[14]), "+f"(d[15]),
        "+f"(d[16]), "+f"(d[17]), "+f"(d[18]), "+f"(d[19]), "+f"(d[20]), "+f"(d[21]), "+f"(d[22]), "+f"(d[23])
      : "r"(da), "n"(HA), "r"(db), "n"(HB), "r"(sc));
  }
};
template <> struct WgSST<80> {
  template <uint32_t HA, uint32_t HB>
  static __device__ __forceinline__ void mma(float* d, uint32_t da, uint32_t db, int sc) {
    asm volatile("{\n.reg .pred p;\n.reg .b64 da, db;\nsetp.ne.b32 p, %44, 0;\n"
      "mov.b64 da, {%40, %41};\nmov.b64 db, {%42, %43};\n"
      "wgmma.mma_async.sync.aligned.m64n80k16.f32.bf16.bf16 {"
      "%0, %1, %2, %3, %4, %5, %6, %7, %8, %9, %10, %11, %12, %13, %14, %15, "
      "%16, %17, %18, %19, %20, %21, %22, %23, %24, %25, %26, %27, %28, %29, %30, %31, "
      "%32, %33, %34, %35, %36, %37, %38, %39"
      "}, da, db, p, 1, 1, 0, 1;\n}\n"
      : "+f"(d[0]), "+f"(d[1]), "+f"(d[2]), "+f"(d[3]), "+f"(d[4]), "+f"(d[5]), "+f"(d[6]), "+f"(d[7]),
        "+f"(d[8]), "+f"(d[9]), "+f"(d[10]), "+f"(d[11]), "+f"(d[12]), "+f"(d[13]), "+f"(d[14]), "+f"(d[15]),
        "+f"(d[16]), "+f"(d[17]), "+f"(d[18]), "+f"(d[19]), "+f"(d[20]), "+f"(d[21]), "+f"(d[22]), "+f"(d[23]),
        "+f"(d[24]), "+f"(d[25]), "+f"(d[26]), "+f"(d[27]), "+f"(d[28]), "+f"(d[29]), "+f"(d[30]), "+f"(d[31]),
        "+f"(d[32]), "+f"(d[33]), "+f"(d[34]), "+f"(d[35]), "+f"(d[36]), "+f"(d[37]), "+f"(d[38]), "+f"(d[39])
      : "r"(da), "n"(HA), "r"(db), "n"(HB), "r"(sc));
  }
};
template <> struct WgSST<192> {
  template <uint32_t HA, uint32_t HB>
  static __device__ __forceinline__ void mma(float* d, uint32_t da, uint32_t db, int sc) {
    asm volatile("{\n.reg .pred p;\n.reg .b64 da, db;\nsetp.ne.b32 p, %100, 0;\n"
      "mov.b64 da, {%96, %97};\nmov.b64 db, {%98, %99};\n"
      "wgmma.mma_async.sync.aligned.m64n192k16.f32.bf16.bf16 {"
      "%0, %1, %2, %3, %4, %5, %6, %7, %8, %9, %10, %11, %12, %13, %14, %15, "
      "%16, %17, %18, %19, %20, %21, %22, %23, %24, %25, %26, %27, %28, %29, %30, %31, "
      "%32, %33, %34, %35, %36, %37, %38, %39, %40, %41, %42, %43, %44, %45, %46, %47, "
      "%48, %49, %50, %51, %52, %53, %54, %55, %56, %57, %58, %59, %60, %61, %62, %63, "
      "%64, %65, %66, %67, %68, %69, %70, %71, %72, %73, %74, %75, %76, %77, %78, %79, "
      "%80, %81, %82, %83, %84, %85, %86, %87, %88, %89, %90, %91, %92, %93, %94, %95"
      "}, da, db, p, 1, 1, 0, 1;\n}\n"
      : "+f"(d[0]), "+f"(d[1]), "+f"(d[2]), "+f"(d[3]), "+f"(d[4]), "+f"(d[5]), "+f"(d[6]), "+f"(d[7]),
        "+f"(d[8]), "+f"(d[9]), "+f"(d[10]), "+f"(d[11]), "+f"(d[12]), "+f"(d[13]), "+f"(d[14]), "+f"(d[15]),
        "+f"(d[16]), "+f"(d[17]), "+f"(d[18]), "+f"(d[19]), "+f"(d[20]), "+f"(d[21]), "+f"(d[22]), "+f"(d[23]),
        "+f"(d[24]), "+f"(d[25]), "+f"(d[26]), "+f"(d[27]), "+f"(d[28]), "+f"(d[29]), "+f"(d[30]), "+f"(d[31]),
        "+f"(d[32]), "+f"(d[33]), "+f"(d[34]), "+f"(d[35]), "+f"(d[36]), "+f"(d[37]), "+f"(d[38]), "+f"(d[39]),
        "+f"(d[40]), "+f"(d[41]), "+f"(d[42]), "+f"(d[43]), "+f"(d[44]), "+f"(d[45]), "+f"(d[46]), "+f"(d[47]),
        "+f"(d[48]), "+f"(d[49]), "+f"(d[50]), "+f"(d[51]), "+f"(d[52]), "+f"(d[53]), "+f"(d[54]), "+f"(d[55]),
        "+f"(d[56]), "+f"(d[57]), "+f"(d[58]), "+f"(d[59]), "+f"(d[60]), "+f"(d[61]), "+f"(d[62]), "+f"(d[63]),
        "+f"(d[64]), "+f"(d[65]), "+f"(d[66]), "+f"(d[67]), "+f"(d[68]), "+f"(d[69]), "+f"(d[70]), "+f"(d[71]),
        "+f"(d[72]), "+f"(d[73]), "+f"(d[74]), "+f"(d[75]), "+f"(d[76]), "+f"(d[77]), "+f"(d[78]), "+f"(d[79]),
        "+f"(d[80]), "+f"(d[81]), "+f"(d[82]), "+f"(d[83]), "+f"(d[84]), "+f"(d[85]), "+f"(d[86]), "+f"(d[87]),
        "+f"(d[88]), "+f"(d[89]), "+f"(d[90]), "+f"(d[91]), "+f"(d[92]), "+f"(d[93]), "+f"(d[94]), "+f"(d[95])
      : "r"(da), "n"(HA), "r"(db), "n"(HB), "r"(sc));
  }
};

struct FftConst {
  uint32_t f[2][4], fi[4][4];
  uint32_t ta[2][2], tb[2][2];
};
__device__ __forceinline__ void cis(int m, float scale, float& c, float& s) {
  const float a = (float)m * (-6.283185307179586f * scale);
  c = __cosf(a);
  s = __sinf(a);
}
__device__ __forceinline__ void fft_tables(uint32_t (&v)[12], int tw) {
  const int row = tw >> 2, ch = tw & 3;
#pragma unroll
  for (int i = 0; i < 4; i++) {
    float c[2], s[2], x[2];
#pragma unroll
    for (int e = 0; e < 2; e++) {
      cis((((32 * (8 * ch + 2 * i + e) + 15) * (4 * row - 63) + 2048) & 4095) - 2048, 1.f / 4096, c[e], s[e]);
      float gc, gs;
      cis((((row & 15) * (8 * (ch & 1) + 2 * i + e) + 8) & 15) - 8, 1.f / 16, gc, gs);
      x[e] = (row >> 4) == (ch >> 1) ? gc : (ch >> 1) ? gs : -gs;
    }
    v[i] = pack2(c[0] * 0.125f, c[1] * 0.125f);
    v[4 + i] = pack2(s[0] * 0.125f, s[1] * 0.125f);
    v[8 + i] = pack2(x[0], x[1]);
  }
#pragma unroll
  for (int i = 0; i < 12; i++) asm volatile("" : "+r"(v[i]));
}
__device__ __forceinline__ void fft_tables_store(const uint32_t (&v)[12], uint32_t sb, int tw) {
  const int row = tw >> 2;
  const uint32_t x = ((tw ^ (row >> 1)) & 3) << 4, a = sb + OFF_FT + (16 * (row >> 3) + (row & 7)) * 64 + x;
  sts128(a, v[0], v[1], v[2], v[3]);
  sts128(a + 512, v[4], v[5], v[6], v[7]);
  sts128(sb + OFF_GT + row * 64 + x, v[8], v[9], v[10], v[11]);
}
__device__ __forceinline__ void fft_twiddles(uint32_t (&v)[2], int tw) {
  float a[2], s[2];
#pragma unroll
  for (int i = 0; i < 2; i++) {
    float c;
    cis((2 * (2 * (tw & 3) + i) - 15) * (4 * (tw >> 2) - 63), 1.f / 4096, c, s[i]);
    a[i] = __fdividef(-s[i], 1.f + c);
  }
  v[0] = pack2(a[0], a[1]);
  v[1] = pack2(s[0], s[1]);
  asm volatile("" : "+r"(v[0]), "+r"(v[1]));
}
__device__ __forceinline__ void fft_matrices(FftConst& k, uint32_t sb, int w, int lane) {
  const uint32_t x = (lane >> 1) & 3;
  const uint2 t0 = lds64(sb + OFF_TT + 256 * w + 8 * lane), t1 = lds64(sb + OFF_TT + 256 * w + 8 * (lane ^ 3));
  k.ta[0][0] = t0.x;
  k.tb[0][0] = t0.y;
  k.ta[1][1] = __byte_perm(t1.x, 0, 0x1032);
  k.tb[1][1] = __byte_perm(t1.y, 0, 0x1032);
#pragma unroll
  for (int j = 0; j < 2; j++) {
    k.ta[1 - j][j] = k.ta[j][j] ^ 0x80008000u;
    k.tb[1 - j][j] = k.tb[j][j] ^ 0x80008000u;
    asm volatile("" : "+r"(k.ta[0][j]), "+r"(k.tb[0][j]), "+r"(k.ta[1][j]), "+r"(k.tb[1][j]));
  }
#pragma unroll
  for (int i = 0; i < 2; i++) {
    ldsm4(k.f[i], sb + OFF_FT + (16 * w + (lane & 15)) * 64 + (((2 * i + (lane >> 4)) ^ x) << 4));
    ldsm4t(k.fi[i], sb + OFF_FT + (32 * i + lane) * 64 + ((w ^ x) << 4));
#pragma unroll
    for (int j = 0; j < 4; j++) {
      k.fi[2 + i][j] = (j & 1) ? k.fi[i][j - 1] ^ 0x80008000u : k.fi[i][j + 1];
      asm volatile("" : "+r"(k.fi[2 + i][j]));
    }
  }
}
__device__ __forceinline__ void rot(uint32_t& x, uint32_t& y, uint32_t a, uint32_t b) {
  x = bfma(a, y, x);
  y = bfma(b, x, y);
  x = bfma(a, y, x);
}
__device__ __forceinline__ void twiddle_fwd(uint32_t (&a)[4][4], float* d, const FftConst& k) {
#pragma unroll
  for (int q = 0; q < 4; q++)
#pragma unroll
    for (int j = 0; j < 2; j++) {
      const float* x = d + 8 * q + 4 * j;
      uint32_t re = pack2(x[0], x[1]), im = pack2(x[2], x[3]);
      rot(re, im, k.ta[0][j], k.tb[0][j]);
      a[q & 2][2 * j + (q & 1)] = re;
      a[(q & 2) + 1][2 * j + (q & 1)] = im;
    }
}
__device__ __forceinline__ void g_step(float* d, const uint32_t (&a)[4][4], uint32_t dre, uint32_t dim) {
  WgRS<32>::set<HI_SW64>(d, a[0], dre);
  WgRS<32>::set<HI_SW64>(d + 16, a[2], dre);
  WgRS<32>::mma<HI_SW64>(d, a[1], dim);
  WgRS<32>::mma<HI_SW64>(d + 16, a[3], dim);
  wg_commit();
}

__device__ __forceinline__ void products(uint32_t (&a)[4][4], const float* H, const float* U, int p) {
#pragma unroll
  for (int j = 0; j < 2; j++)
#pragma unroll
    for (int m = 2 * p; m < 2 * p + 2; m++) {
      float pr[2], pi[2];
#pragma unroll
      for (int x = 0; x < 2; x++)
#pragma unroll
        for (int q = 0; q <= m; q++) {
          const int ih = 16 * (q >> 1) + 2 * (q & 1) + 4 * j + x, iu = 16 * ((m - q) >> 1) + 2 * ((m - q) & 1) + 4 * j + x;
          pr[x] = q ? fmaf(H[ih], U[iu], pr[x]) : H[ih] * U[iu];
          pi[x] = q ? fmaf(H[ih], U[iu + 8], pi[x]) : H[ih] * U[iu + 8];
          pr[x] = fmaf(-H[ih + 8], U[iu + 8], pr[x]);
          pi[x] = fmaf(H[ih + 8], U[iu], pi[x]);
        }
      a[m & 2][2 * j + (m & 1)] = pack2(pr[0], pr[1]);
      a[(m & 2) + 1][2 * j + (m & 1)] = pack2(pi[0], pi[1]);
    }
}

__device__ __forceinline__ void conv_channel(const FftConst& k, uint32_t sb, int c, int wg, int w, int lane) {
  const uint32_t cb = sb + off_ch(c), bars = sb + OFF_BAR;
  const uint32_t du = desc_lo(cb, 1024), dg = desc_lo(sb + OFF_GT, 16), dz = desc_lo(cb + U_BYTES, 16);
  float U[32], H[32];
  uint32_t a[4][4], e[4][4];
  const float dv = __uint_as_float(lds32(sb + OFF_D + 4 * c));
  wg_fence();
  WgRS<64>::set<HI_SW32>(H, k.f[0], du + 256);
  WgRS<64>::mma<HI_SW32>(H, k.f[1], du + 256 + 32);
  wg_commit();
  wg_wait<0>();
  pin<32>(H);
  twiddle_fwd(a, H, k);
  mbar_wait(bars + 8 * (B_U + (c < 3 ? c : 3)), 0);
  TSM(w == 0 && c < 3, 7 + wg);
  wg_fence();
  WgRS<64>::set<HI_SW32>(U, k.f[0], du);
  WgRS<64>::mma<HI_SW32>(U, k.f[1], du + 32);
  wg_commit();
  g_step(H, a, dg, dg + 64);
  wg_wait<1>();
  pin<32>(U);
  twiddle_fwd(e, U, k);
  wg_fence();
  g_step(U, e, dg, dg + 64);
  wg_wait<0>();
  pin<32>(U);
  pin<32>(H);
#pragma unroll
  for (int j = 0; j < 4; j++) H[4 * (j >> 1) + (j & 1)] += dv;
  float V[32];
#pragma unroll
  for (int p = 0; p < 2; p++) {
    products(a, H, U, p);
    wg_fence();
    WgRS<32>::set<HI_SW64>(V + 16 * p, a[2 * p], dg + 64);
    WgRS<32>::mma<HI_SW64>(V + 16 * p, a[2 * p + 1], dg);
    wg_commit();
  }
  const uint32_t za = cb + U_BYTES + (8 * w + (lane & 7)) * 128 + (((lane >> 3) ^ (lane & 7)) << 4);
  const uint32_t ya = cb + (lane >> 4) * 1024 + (8 * w + (lane & 7)) * 32 + ((((lane >> 3) ^ (lane >> 2)) & 1) << 4);
  wg_sync(1 + wg);
#pragma unroll
  for (int p = 0; p < 2; p++) {
    if (p == 0) wg_wait<1>();
    else wg_wait<0>();
    pin<16>(V + 16 * p);
#pragma unroll
    for (int i = 0; i < 4; i++) {
      const int j = i & 1;
      const float* x = V + 16 * p + 4 * j + (i & 2);
      e[p][i] = pack2(x[8], x[9]);
      e[2 + p][i] = pack2(x[0], x[1]);
      rot(e[p][i], e[2 + p][i], k.ta[1][j], k.tb[1][j]);
    }
    stsm4(za ^ (64 * p), e[p]);
    stsm4((za ^ (64 * p)) + 4096, e[2 + p]);
  }
  fence_async_smem();
  wg_sync(1 + wg);
  wg_fence();
  WgRS<64>::set<HI_SW128>(H, k.fi[0], dz);
#pragma unroll
  for (int ks = 1; ks < 4; ks++) WgRS<64>::mma<HI_SW128>(H, k.fi[ks], dz + 128 * ks);
  wg_commit();
  wg_wait<0>();
  pin<32>(H);
  if (lane == 0) mbar_arrive(bars + 8 * B_CVD);
  TSIF(w == 0, 88 + c);
#pragma unroll
  for (int j = 0; j < 8; j++)
    a[j >> 2][j & 3] = j < 2 ? pack2(H[4 * j], H[4 * j + 1]) : pack2(H[4 * j] + H[4 * j - 6], H[4 * j + 1] + H[4 * j - 5]);
  stsm4(ya, a[0]);
  stsm4(ya + 2048, a[1]);
  fence_async_smem();
  __syncwarp();
}

__device__ __forceinline__ void prep_slab(uint4* res, const uint2* sw, uint32_t sb, int slab, int w, int lane) {
  const int t = lane & 3, tp = (lane & 7) >> 1, pos = 8 * tp + 2 * (((lane >> 3) + tp) & 3) + (lane & 1);
  const uint32_t base = sb + OFF_KVS + slab * KVS_BYTES + pos * 128;
  uint32_t kk[2][4][4], vv[2][4];
  mbar_wait(sb + OFF_BAR + 8 * (B_KV + slab), 0);
#pragma unroll
  for (int h = 0; h < 2; h++) {
#pragma unroll
    for (int j = 0; j < 4; j++) {
      const uint32_t a = base + 128 * j;
      ldsm4t(kk[h][j], a + (((w + 4 * h) ^ ((a >> 7) & 7)) << 4));
    }
    const uint32_t a = base + KVS_V;
    ldsm4t(vv[h], a + (((w + 4 * h) ^ ((a >> 7) & 7)) << 4));
  }
#pragma unroll
  for (int h = 0; h < 2; h++) {
    uint32_t (&k)[4][4] = kk[h];
    uint32_t (&v)[4] = vv[h];
    const uint32_t w0 = __byte_perm(sw[h].x, 0, 0x1010), w1 = __byte_perm(sw[h].x, 0, 0x3232);
    const uint32_t w2 = __byte_perm(sw[h].y, 0, 0x1010), w3 = __byte_perm(sw[h].y, 0, 0x3232);
#pragma unroll
    for (int m = 0; m < 4; m++)
      v[m] = bmul(badd(badd(badd(bmul(k[0][m], w3), bmul(k[1][m], w2)), bmul(k[2][m], w1)), bmul(k[3][m], w0)), v[m]);
    uint32_t a[4];
#pragma unroll
    for (int m = 0; m < 4; m++) a[m] = (t & 1) ? v[(m + 3) & 3] : v[m];
    res[h] = (t & 2) ? make_uint4(a[2], a[3], a[0], a[1]) : make_uint4(a[0], a[1], a[2], a[3]);
  }
}

__device__ __forceinline__ void prep_gate(const Params& p, uint32_t sb, int b, int w, int lane) {
  uint2 gw[5], x[4][5];
#pragma unroll
  for (int j = 0; j < 5; j++) gw[j] = ldg64(reinterpret_cast<const uint2*>(p.gate_w) + lane + 32 * j);
#pragma unroll
  for (int i = 0; i < 4; i++)
#pragma unroll
    for (int j = 0; j < 5; j++)
      x[i][j] = ldg64(reinterpret_cast<const uint2*>(p.q) + (16 * b + 4 * w + i) * (DIM / 4) + lane + 32 * j);
  float s[4];
#pragma unroll
  for (int i = 0; i < 4; i++) {
    s[i] = 0.f;
#pragma unroll
    for (int j = 0; j < 5; j++) {
      const uint32_t m0 = bmul(x[i][j].x, gw[j].x), m1 = bmul(x[i][j].y, gw[j].y);
      s[i] += (bf_lo(m0) + bf_hi(m0)) + (bf_lo(m1) + bf_hi(m1));
    }
  }
  const bool h = lane & 16, q = lane & 8;
  const float a = (h ? s[2] : s[0]) + __shfl_xor_sync(0xffffffffu, h ? s[0] : s[2], 16);
  const float c = (h ? s[3] : s[1]) + __shfl_xor_sync(0xffffffffu, h ? s[1] : s[3], 16);
  float z = (q ? c : a) + __shfl_xor_sync(0xffffffffu, q ? a : c, 8);
#pragma unroll
  for (int o = 4; o > 0; o >>= 1) z += __shfl_xor_sync(0xffffffffu, z, o);
  z = bf_lo(pack2(z, 0.f));
  z = bf_lo(pack2(__fdividef(1.f, 1.f + __expf(-z)), 0.f));
  mbar_wait(sb + OFF_BAR + 8 * B_S3, 0);
  if ((lane & 7) == 0) asm volatile("st.shared.f32 [%0], %1;" ::"r"(sb + OFF_GATE + 64 * (b & 7) + 16 * w + (lane >> 1)), "f"(z) : "memory");
  fence_async_smem();
}

__device__ __forceinline__ uint32_t bmax(uint32_t a, uint32_t b) {
  uint32_t d;
  asm("max.bf16x2 %0, %1, %2;" : "=r"(d) : "r"(a), "r"(b));
  return d;
}
__device__ __forceinline__ void softmax_two(const float (&l)[2][2], uint32_t& p0, uint32_t& p1) {
  constexpr float kScale = 0.22360679774997896f, kLog2e = 1.4426950408889634f;
  const uint32_t r0 = pack2(l[0][0], l[1][0]), r1 = pack2(l[0][1], l[1][1]);
  const uint32_t x0 = pack2(bf_lo(r0) * kScale, bf_hi(r0) * kScale), x1 = pack2(bf_lo(r1) * kScale, bf_hi(r1) * kScale);
  uint32_t m = bmax(x0, x1);
  m = bmax(m, __shfl_xor_sync(0xffffffffu, m, 1));
  m = bmax(m, __shfl_xor_sync(0xffffffffu, m, 2));
  const float m0 = bf_lo(m) * kLog2e, m1 = bf_hi(m) * kLog2e;
  p0 = pack2(ex2(bf_lo(x0) * kLog2e - m0), ex2(bf_lo(x1) * kLog2e - m0));
  p1 = pack2(ex2(bf_hi(x0) * kLog2e - m1), ex2(bf_hi(x1) * kLog2e - m1));
}

__device__ __forceinline__ void halo_read(uint32_t (&kpv)[10], uint32_t (&vpv)[10], uint32_t (&tg)[7], const uint4* hp) {
#pragma unroll
  for (int j = 0; j < 7; j++) {
    uint32_t x0, x1, x2;
    asm volatile("ld.relaxed.gpu.global.v4.u32 {%0, %1, %2, %3}, [%4];"
                 : "=r"(x0), "=r"(x1), "=r"(x2), "=r"(tg[j]) : "l"(hp + 32 * j) : "memory");
    if (j < 4) kpv[3 * j] = x0; else vpv[3 * j - 10] = x0;
    if (j < 3) kpv[3 * j + 1] = x1; else vpv[3 * j - 9] = x1;
    if (j < 3) kpv[3 * j + 2] = x2; else if (j < 6) vpv[3 * j - 8] = x2;
  }
}

template <int ROT>
__device__ __forceinline__ void pack_qkv(const float* acc, uint32_t (&qlo)[10], uint32_t (&qhi)[10], uint32_t (&klo)[10],
                                         uint32_t (&khi)[10], uint32_t (&vlo)[10], uint32_t (&vhi)[10]) {
#pragma unroll
  for (int j = 0; j < 10; j++) {
    const int x = (j + ROT) % 10, tq = x < 8 ? x : 16 + x, tk = x < 8 ? 8 + x : 18 + x, tv = x < 8 ? 16 + x : 20 + x;
    khi[j] = pack2(acc[4 * tk + 2], acc[4 * tk + 3]);
    vhi[j] = movm(pack2(acc[4 * tv + 2], acc[4 * tv + 3]));
    qlo[j] = pack2(acc[4 * tq], acc[4 * tq + 1]);
    qhi[j] = pack2(acc[4 * tq + 2], acc[4 * tq + 3]);
    klo[j] = pack2(acc[4 * tk], acc[4 * tk + 1]);
    vlo[j] = pack2(acc[4 * tv], acc[4 * tv + 1]);
    asm volatile("" : "+r"(khi[j]), "+r"(qlo[j]), "+r"(qhi[j]), "+r"(klo[j]), "+r"(vlo[j]));
  }
}

template <int ROT> __device__ __forceinline__ void halo_send(const float* acc, uint4* ho, uint32_t tag) {
#pragma unroll
  for (int j = 0; j < 7; j++) {
    uint32_t x[3];
#pragma unroll
    for (int e = 0; e < 3; e++) {
      const int i = 3 * j + e, y = (i % 10 + ROT) % 10, tk = y < 8 ? 8 + y : 18 + y, tv = y < 8 ? 16 + y : 20 + y;
      x[e] = i < 10 ? pack2(acc[4 * tk + 2], acc[4 * tk + 3]) : i < 20 ? movm(pack2(acc[4 * tv + 2], acc[4 * tv + 3])) : 0u;
    }
    asm volatile("st.relaxed.gpu.global.v4.u32 [%0], {%1, %2, %3, %4};" ::"l"(ho + 32 * j), "r"(x[0]), "r"(x[1]), "r"(x[2]), "r"(tag) : "memory");
  }
}

__device__ __forceinline__ void attention(float* acc, uint32_t sb, int b, int par, int w, int lane, uint32_t tag) {
  const int g = lane >> 2, t = lane & 3;
  uint32_t klo[10], khi[10], vlo[10], vhi[10], qlo[10], qhi[10], kpv[10], vpv[10];
  if (w == 3 && b < NCTA - 8) {
    uint4* ho = g_halo + (b * 2 + par) * 224 + lane;
    if (tail_first(b & 7)) halo_send<8>(acc, ho, tag);
    else halo_send<0>(acc, ho, tag);
    TSIF(par == 0, 76);
    pin<120>(acc);
  }
  if (tail_first(b & 7)) pack_qkv<8>(acc, qlo, qhi, klo, khi, vlo, vhi);
  else pack_qkv<0>(acc, qlo, qhi, klo, khi, vlo, vhi);
  const uint32_t xa = sb + OFF_KVX + (par * 3) * 2560 + lane * 16;
  if (w < 3) {
    sts128(xa + w * 2560, khi[0], khi[1], khi[2], khi[3]);
    sts128(xa + w * 2560 + 512, khi[4], khi[5], khi[6], khi[7]);
    sts128(xa + w * 2560 + 1024, khi[8], khi[9], vhi[0], vhi[1]);
    sts128(xa + w * 2560 + 1536, vhi[2], vhi[3], vhi[4], vhi[5]);
    sts128(xa + w * 2560 + 2048, vhi[6], vhi[7], vhi[8], vhi[9]);
  }
  TSIF(par == 0 && w == 1, 64);
#pragma unroll
  for (int j = 0; j < 10; j++) vlo[j] = movm(vlo[j]);
  const bool far0 = 2 * t > g, far1 = 2 * t + 1 > g;
  const uint32_t mfar = (far0 ? 0x0000FFFFu : 0u) | (far1 ? 0xFFFF0000u : 0u);
  float slo[4][2], lg[2][2];
  uint32_t phi[4], plo[4], qml[4], qmh[4];
#pragma unroll
  for (int h = 0; h < 4; h++) {
    const int f = h == 0 ? 0 : h == 1 ? 3 : h == 2 ? 5 : 8, hf = h < 2 ? 2 : 7;
    const bool mine = (h & 1) ? t >= 2 : t < 2;
    qml[h] = mine ? qlo[hf] : 0u;
    qmh[h] = mine ? qhi[hf] : 0u;
    float a[4] = {0.f, 0.f, 0.f, 0.f}, c[4] = {0.f, 0.f, 0.f, 0.f};
    mma16816(a, qlo[f], qhi[f], qlo[f + 1], qhi[f + 1], klo[f], klo[f + 1]);
    mma16816(c, qlo[f], qhi[f], qlo[f + 1], qhi[f + 1], khi[f], khi[f + 1]);
    mma1688(a, qml[h], qmh[h], klo[hf]);
    mma1688(c, qml[h], qmh[h], khi[hf]);
    slo[h][0] = a[0];
    slo[h][1] = a[1];
    lg[h & 1][0] = far0 ? a[2] : c[2];
    lg[h & 1][1] = far1 ? a[3] : c[3];
    if (h & 1) softmax_two(lg, phi[h - 1], phi[h]);
  }
  TSIF(par == 0 && w == 1, 65);
  wg_sync(1 + par);
  TSIF(par == 0 && w == 1, 66);
  const bool nohist = (w == 0) && (b < 8);
  const uint4* hp = g_halo + ((b - 8) * 2 + par) * 224 + lane;
  uint32_t tg[7];
  if (w > 0) {
    const uint4 v0 = lds128(xa + (w - 1) * 2560), v1 = lds128(xa + (w - 1) * 2560 + 512), v2 = lds128(xa + (w - 1) * 2560 + 1024);
    const uint4 v3 = lds128(xa + (w - 1) * 2560 + 1536), v4 = lds128(xa + (w - 1) * 2560 + 2048);
    kpv[0] = v0.x; kpv[1] = v0.y; kpv[2] = v0.z; kpv[3] = v0.w; kpv[4] = v1.x; kpv[5] = v1.y; kpv[6] = v1.z; kpv[7] = v1.w;
    kpv[8] = v2.x; kpv[9] = v2.y; vpv[0] = v2.z; vpv[1] = v2.w; vpv[2] = v3.x; vpv[3] = v3.y; vpv[4] = v3.z; vpv[5] = v3.w;
    vpv[6] = v4.x; vpv[7] = v4.y; vpv[8] = v4.z; vpv[9] = v4.w;
  } else if (nohist) {
#pragma unroll
    for (int j = 0; j < 10; j++) kpv[j] = vpv[j] = 0u;
  } else {
    TSIF(par == 0, 77);
    halo_read(kpv, vpv, tg, hp);
  }
  if (w == 0 && !nohist) {
    int spins = 0;
    while (true) {
      bool ok = true;
#pragma unroll
      for (int j = 0; j < 7; j++) ok = ok && tg[j] == tag;
      if (__all_sync(0xffffffffu, ok) || ++spins > SPIN_LIMIT) break;
      halo_read(kpv, vpv, tg, hp);
    }
    TSIF(par == 0, 79);
  }
#pragma unroll
  for (int h = 0; h < 4; h++) {
    const int f = h == 0 ? 0 : h == 1 ? 3 : h == 2 ? 5 : 8, hf = h < 2 ? 2 : 7;
    float a[4] = {0.f, 0.f, 0.f, 0.f};
    mma16816(a, qlo[f], qhi[f], qlo[f + 1], qhi[f + 1], kpv[f], kpv[f + 1]);
    mma1688(a, qml[h], qmh[h], kpv[hf]);
    const float ninf = __int_as_float(0xff800000);
    lg[h & 1][0] = far0 ? (nohist ? ninf : a[0]) : slo[h][0];
    lg[h & 1][1] = far1 ? (nohist ? ninf : a[1]) : slo[h][1];
    if (h & 1) softmax_two(lg, plo[h - 1], plo[h]);
  }
  TSIF(par == 0 && w <= 1, 67 + w);
  uint32_t ov[20];
#pragma unroll
  for (int hp = 0; hp < 2; hp++) {
    const int hf = hp ? 7 : 2;
    float sh[4] = {0.f, 0.f, 0.f, 0.f}, i0 = 0.f, i1 = 0.f;
#pragma unroll
    for (int e = 0; e < 2; e++) {
      const int h = 2 * hp + e, f = h == 0 ? 0 : h == 1 ? 3 : h == 2 ? 5 : 8;
      const uint32_t a0 = plo[h] & mfar, a2 = plo[h] & ~mfar, a3 = phi[h] & mfar, c1 = phi[h] & ~mfar;
      float sum[4] = {0.f, 0.f, 0.f, 0.f};
      mma1688(sum, plo[h], phi[h], 0x3F803F80u);
      const float r0 = rcp(sum[0]), r1 = rcp(sum[2]);
#pragma unroll
      for (int j = f; j < f + 2; j++) {
        float o[4] = {0.f, 0.f, 0.f, 0.f};
        mma16816(o, a0, 0u, a2, a3, vpv[j], vlo[j]);
        mma1688(o, 0u, c1, vhi[j]);
        ov[2 * j] = pack2(o[0] * r0, o[1] * r0);
        ov[2 * j + 1] = pack2(o[2] * r1, o[3] * r1);
      }
      const bool mine = e ? g >= 4 : g < 4;
      mma16816(sh, a0, 0u, a2, a3, mine ? vpv[hf] : 0u, mine ? vlo[hf] : 0u);
      mma1688(sh, 0u, c1, mine ? vhi[hf] : 0u);
      if (e == 0 || t >= 2) {
        i0 = r0;
        i1 = r1;
      }
    }
    ov[2 * hf] = pack2(sh[0] * i0, sh[1] * i0);
    ov[2 * hf + 1] = pack2(sh[2] * i1, sh[3] * i1);
  }
  TS(32 + 4 * par + w);
  mbar_wait(sb + OFF_BAR + 8 * B_P1, 0);
  const uint32_t oa = sb + OFF_OA + (lane >> 4) * 2048 + (32 * w + 2 * (lane & 15) + par) * 16;
#pragma unroll
  for (int j = 0; j < 5; j++) stsm4(oa + 4096 * j, ov + 4 * j);
  TSIF(par == 0 && w == 0, 120);
  fence_async_smem();
  TSIF(par == 0 && w == 0, 121);
  __syncwarp();
  if (lane == 0) mbar_arrive(sb + OFF_BAR + 8 * B_ATTN);
  TSM(w == 0 || w == 2, 122 + par + (w == 2 ? 3 : 0));
}

struct Maps {
  CUtensorMap x, wm, wt, k, v, y, wo, qm, qt, om, ot, yl, ol, wh;
};

__device__ __forceinline__ void load_stage(uint32_t sb, int kb, int b, const Maps& m) {
  const uint32_t st = sb + (kb & 3) * STAGE_BYTES, bar = sb + OFF_BAR + 8 * (B_FULL1 + (kb & 3));
  const int r = b >> 3, hg = b & 7, slab = kb - KV_KB;
  const bool kv = slab >= 0 && slab < 5;
  const uint32_t kbar = sb + OFF_BAR + 8 * (B_KV + slab), dst = sb + OFF_KVS + slab * KVS_BYTES;
  mbar_expect_tx(bar, STAGE_BYTES);
  if (kv) mbar_expect_tx(kbar, KVS_BYTES);
  tma_3d(st, &m.x, 64 * kb, 64 * r, 0, bar);
  tma_3d(st + ST_W, &m.wm, 80 * hg + (tail_first(hg) ? 16 : 0), 64 * kb, 0, bar);
  tma_3d(st + ST_WT, &m.wt, 80 * hg + (tail_first(hg) ? 0 : 64), 64 * kb, 0, bar);
  if (kv) tma_3d(dst, &m.k, 0, 32 * (b >> 1) - 3, 2 * slab + (b & 1), kbar);
  if (kv) tma_3d(dst + KVS_V, &m.v, 0, 32 * (b >> 1), 2 * slab + (b & 1), kbar);
}

__global__ void __launch_bounds__(NTHR, 1) fused_kernel(const __grid_constant__ Maps m, const Params p) {
  extern __shared__ __align__(1024) uint8_t smem[];
  const uint32_t sb = (uint32_t)__cvta_generic_to_shared(smem);
  const uint32_t bars = sb + OFF_BAR;
  const int tid = threadIdx.x, lane = tid & 31;
  int b = blockIdx.x;
  b = (((b & 63) >> 3) * 2 + (b & 1)) * 8 + (((b < 64 ? 0x6521 : 0x7430) >> (4 * ((b >> 1) & 3))) & 7);
  const int r = b >> 3, hg = b & 7;

  if (tid == T_ISSUE) {
    TSM(true, 0);
#pragma unroll
    for (int i = 0; i < NS0; i++) mbar_init(bars + 8 * (B_F0 + (i ? 4 + i : 0)), 1);
    fence_async_smem();
#pragma unroll
    for (int i = 0; i < NS0; i++) {
      const uint32_t fb = bars + 8 * (B_F0 + (i ? 4 + i : 0));
      mbar_expect_tx(fb, (i ? 0 : ST_W) + 24576 / NS0);
      if (i == 0 && !W_FIRST) tma_3d(sb, &m.x, 0, 64 * r, 0, fb);
      tma_3d(sb + ST_W + 24576 / NS0 * i, NS0 > 1 ? &m.wh : &m.wm, 80 * hg + (tail_first(hg) ? 16 : 0), 64 / NS0 * i, 0, fb);
      if (i == 0 && W_FIRST) tma_3d(sb, &m.x, 0, 64 * r, 0, fb);
    }
#pragma unroll
    for (int i = 0; i < 4; i++) mbar_init(bars + 8 * (B_FULL1 + i), 1);
    if (SPLIT1) mbar_init(bars + 8 * B_F1, 1);
    fence_async_smem();
    mbar_expect_tx(bars + 8 * B_FULL1, STAGE_BYTES - ST_WT);
    tma_3d(sb + ST_WT, &m.wt, 80 * hg + (tail_first(hg) ? 0 : 64), 0, 0, bars + 8 * B_FULL1);
    if (SPLIT1) {
      mbar_expect_tx(bars + 8 * B_F1, ST_WT);
      tma_3d(sb + STAGE_BYTES, &m.x, 64, 64 * r, 0, bars + 8 * B_F1);
      tma_3d(sb + STAGE_BYTES + ST_W, &m.wm, 80 * hg + (tail_first(hg) ? 16 : 0), 64, 0, bars + 8 * B_F1);
      mbar_expect_tx(bars + 8 * (B_FULL1 + 1), STAGE_BYTES - ST_WT);
      tma_3d(sb + STAGE_BYTES + ST_WT, &m.wt, 80 * hg + (tail_first(hg) ? 0 : 64), 64, 0, bars + 8 * (B_FULL1 + 1));
    } else {
      load_stage(sb, 1, b, m);
    }
  } else if (tid == T_INIT) {
#pragma unroll
    for (int i = 0; i < B_F0; i++) mbar_init(bars + 8 * i, i < B_GATE ? 8 : i < B_CVD ? 4 : i == B_CVD ? 20 : 1);
    fence_async_smem();
  }
  const int warp = __shfl_sync(0xffffffffu, tid >> 5, 0), wg = warp >> 2, w = warp & 3;
  __syncthreads();

  if (wg == 3) {
    asm volatile("setmaxnreg.dec.sync.aligned.u32 56;");
    if (w == 0) {
      if (lane == 0) {
#pragma unroll 1
        for (int kb = 2; kb < 10; kb++) {
          if (kb >= 4) mbar_wait(bars + 8 * (kb == 7 ? B_E3 : B_EMPTY1 + (kb & 3)), (kb >> 3) & 1);
          TSIF(kb >= 4, 44 + kb);
          load_stage(sb, kb, b, m);
          TSIF(kb == 3, 60);
          if (kb == 9) mbar_arrive(bars + 8 * B_LAST);
        }
        mbar_wait(bars + 8 * B_WOP, 0);
        mbar_wait(bars + 8 * B_EPOCH, 0);
        flag_wait(g_cnt + C_W + 32 * hg, (lds32(sb + OFF_EPOCH) + 1) * 16);
        TS(30);
#pragma unroll 1
        for (int j = 0; j < 8; j++) {
          if (j >= 6) mbar_wait(bars + 8 * (B_EMPTY2 + j - 6), 0);
          if (j == 4) mbar_wait(bars + 8 * B_ORB, 0);
          TSIF(j >= 6, 100 + j);
          mbar_expect_tx(bars + 8 * (B_FULL2 + j), j == 0 ? WO_BYTES : j == 5 ? O_BYTES + WO_BYTES + 512 : O_BYTES + WO_BYTES);
          bulk_load(sb + off_w(j), g_WO + (hg * 8 + step_src(hg, j)) * 800, WO_BYTES, bars + 8 * (B_FULL2 + j));
        }
        mbar_wait(bars + 8 * (B_EMPTY2 + 3), 0);
        mbar_expect_tx(bars + 8 * B_QF, O_BYTES);
        tma_2d(sb + OFF_QS, &m.qm, 80 * hg, 128 * r, bars + 8 * B_QF);
        tma_2d(sb + OFF_QT, &m.qt, 80 * hg + 64, 128 * r, bars + 8 * B_QF);
      }
    } else if (w == 1) {
      unsigned epoch = 0;
      if (lane == 0) {
        epoch = atomicAdd(g_cnt + C_LAUNCH, 1u) / NCTA;
        asm volatile("st.shared.u32 [%0], %1;" ::"r"(sb + OFF_EPOCH), "r"(epoch) : "memory");
        mbar_arrive(bars + 8 * B_EPOCH);
        mbar_wait(bars + 8 * B_KVD, 0);
        mbar_expect_tx(bars + 8 * B_HB, 5 * 4096);
#pragma unroll 1
        for (int c = 0; c < 5; c++) {
          if (c == 3) mbar_wait(bars + 8 * B_S3, 0);
          bulk_load(sb + off_ch(c) + U_BYTES, p.ssm_k + (5 * b + c) * SEQ, 4096, bars + 8 * B_HB);
        }
#pragma unroll
        for (int c = 0; c < 4; c++) mbar_expect_tx(bars + 8 * (B_U + c), c < 3 ? U_BYTES : 2 * U_BYTES);
        const uint4* usrc = g_U + 5 * b * U_PITCH;
        mbar_wait(bars + 8 * B_USIG, 0);
        flag_wait(g_cnt + C_PREP + 32 * (b & 15), (epoch + 1) * NCTA);
        TS(23);
#pragma unroll
        for (int c = 0; c < 5; c++) {
          if (c == 3) mbar_wait(bars + 8 * (B_U + 2), 0);
          bulk_load(sb + off_ch(c), usrc + c * U_PITCH, U_BYTES, bars + 8 * (B_U + (c < 3 ? c : 3)));
          TSIF(c == 0 || c == 4, 116 + (c >> 2));
        }
      }
      epoch = __shfl_sync(0xffffffffu, epoch, 0);
      if (lane < 8) {
        const int src = (b & ~7) | step_src(hg, lane);
        mbar_wait(bars + 8 * B_ATTN, 0);
        TS(20);
        bool seen = false;
#pragma unroll 1
        for (int spins = 0; spins < SPIN_LIMIT; spins++) {
          const bool now = !seen && (int)(flag_read(g_cnt + C_O + 32 * src) - (epoch + 1)) >= 0;
          if (now && lane >= 1 && lane < 4) bulk_load(sb + off_o(lane), g_O + src * 1280, O_BYTES, bars + 8 * (B_FULL2 + lane));
          seen = seen || now;
          if (__all_sync(0xff, seen)) break;
        }
        TS(21);
        if (lane == 5) bulk_load(sb + OFF_GATE, g_gate + 128 * r, 512, bars + 8 * (B_FULL2 + 5));
#pragma unroll 1
        for (int j = 4; j < 8; j++) {
          if (lane == j) {
            mbar_wait(bars + 8 * (j < 6 ? B_C34 : B_EMPTY2 + j - 6), 0);
            bulk_load(sb + off_o(j), g_O + src * 1280, O_BYTES, bars + 8 * (B_FULL2 + j));
          }
          __syncwarp(0xff);
        }
        TS(22);
      }
    } else if (w == 2) {
      mbar_wait(bars + 8 * B_PREP, 0);
      flag_signal(g_cnt + C_PREP, 16, lane);
      TS(25);
      if (lane == 0) {
        mbar_arrive(bars + 8 * B_USIG);
        mbar_expect_tx(bars + 8 * B_ORB, O_BYTES / 4 + 64);
        mbar_wait(bars + 8 * B_GATE, 0);
        publish(g_gate + 16 * b, sb + OFF_GATE + 64 * hg, 64);
        bulk_load(sb + OFF_GATE + 64 * hg, g_gate + 16 * b, 64, bars + 8 * B_ORB);
        mbar_wait(bars + 8 * B_ATTN, 0);
        publish(g_O + b * 1280, sb + OFF_OA, O_BYTES);
        tma_2d(sb + OFF_KVX + 10240, &m.ol, 48, b * 160, bars + 8 * B_ORB);
        TS(74);
        mbar_wait(bars + 8 * B_ORB, 0);
        flag_bump(g_cnt + C_O + 32 * b);
        TS(26);
      }
    } else {
      if (lane == 0) {
        uint4* dst = g_WO + (hg * 8 + (r >> 1)) * 800 + (r & 1) * 80;
        mbar_wait(bars + 8 * B_S3, 0);
        asm volatile("cp.async.bulk.prefetch.L2.global [%0], 6400;" ::"l"(p.wo + b * 3200) : "memory");
        mbar_wait(bars + 8 * B_P1, 0);
        mbar_wait(bars + 8 * WB_TRIG, 0);
        mbar_expect_tx(bars + 8 * B_WST, WO_BYTES / 2);
        tma_3d(sb + OFF_WA, &m.wo, 0, 40 * r, 5 * hg, bars + 8 * B_WST);
        mbar_wait(bars + 8 * B_WST, 0);
#pragma unroll 1
        for (int n = 0; n < 5; n++) bulk_store(dst + 160 * n, sb + OFF_WA + 1280 * n, 1280);
        bulk_wait_read();
        mbar_expect_tx(bars + 8 * B_WST, WO_BYTES / 2);
#pragma unroll 1
        for (int n = 0; n < 5; n++) bulk_load(sb + OFF_WA + 1280 * n, dst + 160 * n, 1280, bars + 8 * B_WST);
        mbar_wait(bars + 8 * B_WST, 1);
        flag_bump(g_cnt + C_W + 32 * hg);
        mbar_arrive(bars + 8 * B_WOP);
        TS(71);
        mbar_expect_tx(bars + 8 * B_C34, 3 * (U_BYTES / 4));
        mbar_expect_tx(bars + 8 * B_YRB, 2 * (U_BYTES / 4));
#pragma unroll 1
        for (int c = 0; c < 5; c++) {
          mbar_wait(bars + 8 * (B_YST + c), 0);
          publish(g_U + (5 * b + c) * U_PITCH, sb + off_ch(c), U_BYTES);
          tma_2d(sb + off_ch(c), &m.yl, 48, (5 * b + c) * (U_PITCH / 8), bars + 8 * (c < 3 ? B_C34 : B_YRB));
        }
        TS(75);
        mbar_wait(bars + 8 * B_C34, 0);
        mbar_wait(bars + 8 * B_YRB, 0);
        flag_bump(g_cnt + C_Y + 32 * (b >> 4));
        TS(27);
        mbar_expect_tx(bars + 8 * B_YFULL, 20480);
        flag_wait(g_cnt + C_Y + 32 * hg, (lds32(sb + OFF_EPOCH) + 1) * 16);
        TS(24);
        tma_2d(sb + OFF_YT, &m.y, 128 * r, 80 * hg, bars + 8 * B_YFULL);
        tma_2d(sb + OFF_YT + 10240, &m.y, 128 * r + 64, 80 * hg, bars + 8 * B_YFULL);
      }
    }
  } else {
    asm volatile("setmaxnreg.inc.sync.aligned.u32 152;");
    if (wg < 2) {
      float acc[120];
#pragma unroll
      for (int i = 0; i < 120; i++) acc[i] = 0.f;
      const uint32_t da = desc_lo(sb + wg * 8192, 16), db = desc_lo(sb + ST_W, 8192), dc = desc_lo(sb + ST_WT, 2048);
      mbar_wait(bars + 8 * B_F0, 0);
      TSIF(w == 0 && wg == 0, 1);
      wg_fence();
#pragma unroll
      for (int k = 0; k < 4; k++) {
        constexpr int KP = 4 / NS0;
        if (k && k % KP == 0) {
          wg_commit();
          mbar_wait(bars + 8 * (B_F0 + 4 + k / KP), 0);
          wg_fence();
        }
        WgSST<192>::mma<HI_SW128, HI_SW128>(acc, da + 2 * k, desc_lo(sb + ST_W, 8192 / NS0) + 128 * (k % KP) + 1536 / NS0 * (k / KP), 1);
      }
      wg_commit();
      mbar_wait(bars + 8 * B_FULL1, 0);
      wg_fence();
#pragma unroll
      for (int k = 0; k < 4; k++) WgSST<48>::mma<HI_SW128, HI_SW32>(acc + 96, da + 2 * k, dc + 32 * k, 1);
      wg_commit();
      if (SPLIT1) {
        constexpr uint32_t so = STAGE_BYTES >> 4;
        mbar_wait(bars + 8 * B_F1, 0);
        wg_fence();
#pragma unroll
        for (int k = 0; k < 4; k++) WgSST<192>::mma<HI_SW128, HI_SW128>(acc, da + so + 2 * k, db + so + 128 * k, 1);
        wg_commit();
        wg_wait<1>();
        if (lane == 0) mbar_arrive(bars + 8 * B_EMPTY1);
        mbar_wait(bars + 8 * (B_FULL1 + 1), 0);
        wg_fence();
#pragma unroll
        for (int k = 0; k < 4; k++) WgSST<48>::mma<HI_SW128, HI_SW32>(acc + 96, da + so + 2 * k, dc + so + 32 * k, 1);
        wg_commit();
      }
#pragma unroll 1
      for (int kb = 1 + SPLIT1; kb < 10; kb++) {
        mbar_wait(bars + 8 * (B_FULL1 + (kb & 3)), (kb >> 2) & 1);
        const uint32_t so = (kb & 3) * (STAGE_BYTES >> 4);
        wg_fence();
#pragma unroll
        for (int k = 0; k < 4; k++) {
          WgSST<192>::mma<HI_SW128, HI_SW128>(acc, da + so + 2 * k, db + so + 128 * k, 1);
          WgSST<48>::mma<HI_SW128, HI_SW32>(acc + 96, da + so + 2 * k, dc + so + 32 * k, 1);
        }
        wg_commit();
        wg_wait<1>();
        if (lane == 0) mbar_arrive(bars + 8 * (kb == 4 ? B_E3 : B_EMPTY1 + ((kb - 1) & 3)));
      }
      mbar_wait(bars + 8 * B_EPOCH, 0);
      const uint32_t tag = lds32(sb + OFF_EPOCH) + 1;
      mbar_wait(bars + 8 * B_S3, 0);
      wg_wait<0>();
      pin<120>(acc);
      if (lane == 0) mbar_arrive(bars + 8 * B_P1);
      TSM(w == 0, 3 + wg);
      attention(acc, sb, b, wg, w, lane, tag);
    } else {
      const int tw = tid & 127, chl = 64 * (b & 1) + 8 * w + (lane >> 2);
      uint4* up = g_U + chl * U_PITCH + ((4 * (b >> 1) + (lane & 3)) ^ ((b >> 2) & 1));
      uint2 sw[10];
      uint32_t dv = 0;
      if (lane < 5) dv = __ldg(reinterpret_cast<const unsigned short*>(p.ssm_D) + 5 * b + lane);
#pragma unroll
      for (int i = 0; i < 10; i++) sw[i] = ldg64(reinterpret_cast<const uint2*>(p.shift_k) + chl + 128 * (i >> 1) + 32 * (i & 1));
      uint32_t tab[12];
      uint32_t tt[2];
      fft_tables(tab, tw);
      fft_twiddles(tt, tw);
      uint4 res[10];
#pragma unroll
      for (int i = 0; i < 10; i++) res[i] = make_uint4(0, 0, 0, 0);
#pragma unroll 1
      for (int slab = 0; slab < 5; slab++) {
#pragma unroll
        for (int i = 0; i < 8; i++) res[i] = res[i + 2];
        prep_slab(res + 8, sw, sb, slab, w, lane);
        TSIF(w == 0, 99 + 4 * slab);
#pragma unroll
        for (int i = 0; i < 8; i++) sw[i] = sw[i + 2];
      }
      TSIF(w == 0, 28);
      __syncwarp();
      if (lane == 0) mbar_arrive(bars + 8 * B_KVD + ((res[8].x ^ res[9].x) & p.zero));
      mbar_wait(bars + 8 * B_KVD, 0);
      fft_tables_store(tab, sb, tw);
      mbar_wait(bars + 8 * B_LAST, 0);
#pragma unroll
      for (int i = 0; i < 10; i++) up[(128 * (i >> 1) + 32 * (i & 1)) * U_PITCH] = res[i];
      __syncwarp();
      if (lane == 0) mbar_arrive(bars + 8 * B_PREP);
      TSIF(w == 0, 5);
      mbar_wait(bars + 8 * B_LAST, 0);
      prep_gate(p, sb, b, w, lane);
      __syncwarp();
      if (lane == 0) mbar_arrive(bars + 8 * B_GATE);
      TSIF(w == 0, 72);
      mbar_wait(bars + 8 * B_HB, 0);
      TSIF(w == 0, 2);
      const uint32_t ha = sb + U_BYTES + ((tw >> 3) * 16 + 8 + (tw & 7)) * 16;
      uint4 hv[5];
#pragma unroll
      for (int c = 0; c < 5; c++) hv[c] = lds128(ha + off_ch(c));
      __syncwarp();
#pragma unroll
      for (int c = 0; c < 5; c++) sts128((ha ^ 16) + off_ch(c), hv[c].x, hv[c].y, hv[c].z, hv[c].w);
      asm volatile("st.shared.v2.u32 [%0], {%1, %2};" ::"r"(sb + OFF_TT + 8 * tw), "r"(tt[0]), "r"(tt[1]) : "memory");
      if (tw < 5) asm volatile("st.shared.f32 [%0], %1;" ::"r"(sb + OFF_D + 4 * tw), "f"(bf_lo(dv) * 0.125f) : "memory");
      fence_async_smem();
      __syncwarp();
      if (lane == 0) mbar_arrive(bars + 8 * B_HA);
      TSIF(w == 0, 6);
    }

    FftConst fc;
    TSM(w == 0 && wg == 0, 104);
    mbar_wait(bars + 8 * B_HA, 0);
    fft_matrices(fc, sb, w, lane);
    TSM(w == 0 && wg == 0, 105);
    TSM(w == 0 && wg == 2, 124);
#pragma unroll 1
    for (uint32_t tasks = wg == 0 ? TASK0 : wg == 1 ? TASK1 : TASK2; tasks; tasks >>= 4) {
      const int c = (tasks & 7) - 1;
      conv_channel(fc, sb, c, wg, w, lane);
      if (lane == 0) mbar_arrive(bars + 8 * (B_YST + c));
      TSM(w == 0, 10 + c);
    }

    if (wg != 1) {
      const int wg = warp >> 3;
      const int g = lane >> 2;
      float acc[40];
#pragma unroll
      for (int i = 0; i < 40; i++) acc[i] = 0.f;
      const uint32_t da = desc_lo(sb + wg * 1024, 2048), db = desc_lo(sb, 2560);
      mbar_wait(bars + 8 * B_ORB, 0);
      mbar_wait(bars + 8 * B_FULL2, 0);
      TSM(w == 0, 15 + wg);
#pragma unroll 1
      for (int j = 0; j < 8; j++) {
        if (j == 1 - wg) mbar_wait(bars + 8 * B_CVD, 0);
        mbar_wait(bars + 8 * (B_FULL2 + j), 0);
        TSM(w == 0 && wg == 0, 44 + (j < 4 ? j : j + 6));
        const uint32_t oa = da + (off_o(j) >> 4), ob = db + (off_w(j) >> 4);
        wg_fence();
#pragma unroll
        for (int k = 0; k < 5; k++) WgSST<80>::mma<HI_NONE, HI_SW32>(acc, oa + 256 * k, ob + 32 * k, 1);
        wg_commit();
        wg_wait<1>();
        if (j >= 1 && j <= 4 && lane == 0) mbar_arrive(bars + 8 * (B_EMPTY2 + j - 1));
      }
      TSIF(w == 0 && wg == 0, 113);
      const int tr = 64 * wg + 16 * w + (lane & 15);
      const uint32_t fm = sb + OFF_QS + tr * 128, fx = (lane >> 4) ^ (tr & 7);
      const uint32_t ft = sb + OFF_QT + tr * 32 + (((lane >> 4) ^ (tr >> 2)) & 1) * 16;
      const float g0 = __uint_as_float(lds32(sb + OFF_GATE + (64 * wg + 16 * w + g) * 4));
      const float g1 = __uint_as_float(lds32(sb + OFF_GATE + (64 * wg + 16 * w + 8 + g) * 4));
      const uint32_t ga = pack2(g0, g0), gb = pack2(g1, g1);
      const uint32_t na = pack2(1.f - g0, 1.f - g0), nb = pack2(1.f - g1, 1.f - g1);

      uint32_t qf[20];
      mbar_wait(bars + 8 * B_QF, 0);
      TSM(w == 0 && wg == 0, 99);
#pragma unroll
      for (int j = 0; j < 5; j++) ldsm4(qf + 4 * j, j < 4 ? fm + ((fx ^ (2 * j)) << 4) : ft);
#pragma unroll
      for (int i = 0; i < 20; i++) {
        qf[i] = bmul((i & 1) ? gb : ga, qf[i]);
        asm volatile("" : "+r"(qf[i]));
      }

      wg_wait<0>();
      pin<40>(acc);
      TSM(w == 0, 17 + wg);
      uint32_t pb[20];
#pragma unroll
      for (int j = 0; j < 10; j++) {
        pb[2 * j] = bmul(na, pack2(acc[4 * j], acc[4 * j + 1]));
        pb[2 * j + 1] = bmul(nb, pack2(acc[4 * j + 2], acc[4 * j + 3]));
        asm volatile("" : "+r"(pb[2 * j]), "+r"(pb[2 * j + 1]));
      }
      const uint32_t ya = sb + OFF_YT + wg * 10240 + ((lane >> 4) * 8 + (lane & 7)) * 128 +
                          (((2 * w + (((lane >> 3) & 1) ^ wg)) ^ (lane & 7)) << 4);
      mbar_wait(bars + 8 * B_YFULL, 0);
      TSM(w == 0 && wg == 0, 19);
#pragma unroll
      for (int j = 0; j < 5; j++) {
        uint32_t y[4];
        ldsm4t(y, ya + 2048 * j);
#pragma unroll
        for (int i = 0; i < 4; i++)
          qf[4 * j + i] = bfma(qf[4 * j + i], y[i], pb[4 * j + i]);
      }
#pragma unroll
      for (int j = 0; j < 5; j++) stsm4(j < 4 ? fm + ((fx ^ (2 * j)) << 4) : ft, qf + 4 * j);
      fence_async_smem();
      __syncwarp();
      if (lane == 0) {
        const int row = 64 * wg + 16 * w;
        asm volatile("cp.async.bulk.tensor.2d.global.shared::cta.bulk_group [%0, {%2, %3}], [%1];"
                     ::"l"(&m.om), "r"(sb + OFF_QS + row * 128), "r"(80 * hg), "r"(128 * r + row) : "memory");
        asm volatile("cp.async.bulk.tensor.2d.global.shared::cta.bulk_group [%0, {%2, %3}], [%1];"
                     ::"l"(&m.ot), "r"(sb + OFF_QT + row * 32), "r"(80 * hg + 64), "r"(128 * r + row) : "memory");
        asm volatile("cp.async.bulk.commit_group;\ncp.async.bulk.wait_group.read 0;" ::: "memory");
      }
      TSM(w == 0 || w == 3, 40 + 2 * wg + (w & 1));
    }
  }
}

typedef CUresult (*EncodeFn)(CUtensorMap*, CUtensorMapDataType, cuuint32_t, void*, const cuuint64_t*, const cuuint64_t*,
                             const cuuint32_t*, const cuuint32_t*, CUtensorMapInterleave, CUtensorMapSwizzle,
                             CUtensorMapL2promotion, CUtensorMapFloatOOBfill);

void encode(EncodeFn fn, CUtensorMap* tm, const void* base, int rank, const cuuint64_t* dims, const cuuint64_t* strides,
            const cuuint32_t* box, CUtensorMapSwizzle swz) {
  const cuuint32_t ones[3] = {1, 1, 1};
  fn(tm, CU_TENSOR_MAP_DATA_TYPE_BFLOAT16, rank, const_cast<void*>(base), dims, strides, box, ones,
     CU_TENSOR_MAP_INTERLEAVE_NONE, swz, CU_TENSOR_MAP_L2_PROMOTION_L2_128B, CU_TENSOR_MAP_FLOAT_OOB_FILL_NONE);
}

}

extern "C" void kernel_launch(void* const* d_in, const int* in_sizes, int n_in, void* d_out, int out_size) {
  (void)in_sizes; (void)n_in; (void)out_size;
  Params p;
  p.q = (const __nv_bfloat16*)d_in[0];
  p.k = (const __nv_bfloat16*)d_in[1];
  p.v = (const __nv_bfloat16*)d_in[2];
  p.shift_k = (const __nv_bfloat16*)d_in[3];
  p.ssm_k = (const __nv_bfloat16*)d_in[4];
  p.ssm_D = (const __nv_bfloat16*)d_in[5];
  p.wqkv = (const __nv_bfloat16*)d_in[7];
  p.wo = (const __nv_bfloat16*)d_in[8];
  p.gate_w = (const __nv_bfloat16*)d_in[9];
  p.out = (__nv_bfloat16*)d_out;
  p.zero = 0;

  static EncodeFn fn = nullptr;
  static void *yaddr = nullptr, *oaddr = nullptr;
  if (!fn) {
    cudaDriverEntryPointQueryResult qr;
    void* f = nullptr;
    cudaGetDriverEntryPoint("cuTensorMapEncodeTiled", &f, cudaEnableDefault, &qr);
    fn = (EncodeFn)f;
    cudaGetSymbolAddress(&yaddr, g_U);
    cudaGetSymbolAddress(&oaddr, g_O);
    cudaFuncSetAttribute(fused_kernel, cudaFuncAttributeMaxDynamicSharedMemorySize, SMEM_BYTES);
  }
  Maps m;
  {
    const cuuint64_t dims[3] = {640, 1024, 2}, st[2] = {2560, 1280};
    const cuuint32_t box[3] = {64, 64, 2};
    encode(fn, &m.x, p.q, 3, dims, st, box, CU_TENSOR_MAP_SWIZZLE_128B);
  }
  {
    const cuuint64_t dims[3] = {640, 640, 3}, st[2] = {3840, 1280};
    const cuuint32_t box[3] = {64, 64, 3}, boxt[3] = {16, 64, 3};
    encode(fn, &m.wm, p.wqkv, 3, dims, st, box, CU_TENSOR_MAP_SWIZZLE_128B);
    encode(fn, &m.wt, p.wqkv, 3, dims, st, boxt, CU_TENSOR_MAP_SWIZZLE_32B);
    const cuuint32_t boxh[3] = {64, 64 / NS0, 3};
    encode(fn, &m.wh, p.wqkv, 3, dims, st, boxh, CU_TENSOR_MAP_SWIZZLE_128B);
  }
  {
    const cuuint64_t dims[3] = {64, 2048, 10}, st[2] = {1280, 128};
    const cuuint32_t boxk[3] = {64, 35, 1}, boxv[3] = {64, 32, 1};
    encode(fn, &m.k, p.k, 3, dims, st, boxk, CU_TENSOR_MAP_SWIZZLE_128B);
    encode(fn, &m.v, p.v, 3, dims, st, boxv, CU_TENSOR_MAP_SWIZZLE_128B);
  }
  {
    const cuuint64_t dims[3] = {16, 640, 40}, st[2] = {1280, 32};
    const cuuint32_t box[3] = {16, 40, 5};
    encode(fn, &m.wo, p.wo, 3, dims, st, box, CU_TENSOR_MAP_SWIZZLE_32B);
  }
  {
    const cuuint64_t dims[2] = {2048, 640}, st[1] = {U_PITCH * 16};
    const cuuint32_t box[2] = {64, 80};
    encode(fn, &m.y, yaddr, 2, dims, st, box, CU_TENSOR_MAP_SWIZZLE_128B);
    const cuuint64_t dl[2] = {64, DIM * U_PITCH / 8}, dol[2] = {64, NCTA * 160}, sl[1] = {128};
    const cuuint32_t bl[2] = {16, 32}, bol[2] = {16, 160};
    encode(fn, &m.yl, yaddr, 2, dl, sl, bl, CU_TENSOR_MAP_SWIZZLE_NONE);
    encode(fn, &m.ol, oaddr, 2, dol, sl, bol, CU_TENSOR_MAP_SWIZZLE_NONE);
  }
  {
    const cuuint64_t dims[2] = {640, 2048}, st[1] = {1280};
    const cuuint32_t bqm[2] = {64, 128}, bqt[2] = {16, 128}, bom[2] = {64, 16}, bot[2] = {16, 16};
    encode(fn, &m.qm, p.q, 2, dims, st, bqm, CU_TENSOR_MAP_SWIZZLE_128B);
    encode(fn, &m.qt, p.q, 2, dims, st, bqt, CU_TENSOR_MAP_SWIZZLE_32B);
    encode(fn, &m.om, p.out, 2, dims, st, bom, CU_TENSOR_MAP_SWIZZLE_128B);
    encode(fn, &m.ot, p.out, 2, dims, st, bot, CU_TENSOR_MAP_SWIZZLE_32B);
  }
  fused_kernel<<<NCTA, NTHR, SMEM_BYTES>>>(m, p);
}
```

```cpp
#include <cuda.h>
#include <cuda_bf16.h>
#include <cuda_runtime.h>
#include <stdint.h>

namespace {

constexpr int SEQ = 2048, DIM = 640, NCTA = 128, NTHR = 512;

#define KV_KB 2
#define DEV_EXIT 0
#define FENCE_LO 0
#define FENCE_HI 0
#define WB_TRIG B_USIG
#define T_ISSUE 288
#define T_INIT 448
#define TASK0 0x3
#define TASK1 0x52
#define TASK2 0x41

constexpr uint32_t STAGE_BYTES = 47104, ST_W = 16384, ST_WT = 40960;
constexpr uint32_t O_BYTES = 20480, WO_BYTES = 12800;
constexpr uint32_t OFF_OA = 0;
constexpr uint32_t OFF_QS = 3 * O_BYTES, OFF_QT = OFF_QS + 16384;
constexpr uint32_t OFF_WC = 81920;
constexpr uint32_t OFF_WA = 94720;
constexpr uint32_t OFF_GATE = 145920;
constexpr uint32_t OFF_TT = 146432;
constexpr uint32_t OFF_KVX = 148480;
constexpr uint32_t OFF_CH3 = 163840;
constexpr uint32_t CH_BYTES = 12288, U_BYTES = 4096;
constexpr uint32_t OFF_FT = 225280, OFF_GT = 229376;
constexpr uint32_t OFF_CH0 = 188416;
constexpr uint32_t OFF_KVS = OFF_CH0, KVS_V = 4480, KVS_BYTES = 8576;
constexpr uint32_t OFF_YT = 163840;
constexpr uint32_t OFF_BAR = 231936;
constexpr uint32_t SMEM_BYTES = OFF_BAR + 512;

enum : uint32_t {
  B_EMPTY1 = 0, B_S3 = 3, B_E3 = 4, B_EMPTY2 = 5, B_ATTN = 9, B_P1 = 10,
  B_GATE = 11, B_HA = 12, B_KVD = 13, B_PREP = 14, B_YST = 15,
  B_CVD = 20,
  B_FULL2 = 21, B_U = 29, B_KV = 33, B_HB = 38, B_C34 = 39, B_YRB = 40, B_YFULL = 41, B_EPOCH = 42, B_LAST = 43,
  B_WOP = 44, B_USIG = 45, B_WST = 46, B_QF = 47, B_ORB = 48,
  B_F0 = 49, B_FULL1 = 53
};
constexpr uint32_t OFF_EPOCH = OFF_BAR + 8 * 58, OFF_D = OFF_BAR + 8 * 60;
__device__ __forceinline__ uint32_t off_o(int j) { return j < 4 ? OFF_OA + j * O_BYTES : j < 6 ? OFF_CH0 + (j - 4) * O_BYTES : OFF_OA + (j - 6) * O_BYTES; }
__device__ __forceinline__ uint32_t off_w(int j) { return j < 4 ? OFF_WA + j * WO_BYTES : j == 4 ? OFF_KVX : j == 5 ? OFF_WC : OFF_WA + (j - 6) * WO_BYTES; }
__device__ __forceinline__ int step_src(int hg, int j) { return j == 0 ? hg : j <= hg ? j - 1 : j; }
__device__ __forceinline__ bool tail_first(int hg) { return (hg & 3) == 3; }
__device__ __forceinline__ uint32_t off_ch(int c) { return (c < 3 ? OFF_CH0 : OFF_CH3 - 3 * CH_BYTES) + c * CH_BYTES; }

#define U_PITCH 264
__device__ __align__(1024) uint4 g_U[DIM * U_PITCH];
__device__ __align__(128) uint4 g_O[NCTA * 1280];
__device__ uint4 g_WO[64 * 800];
__device__ uint4 g_halo[NCTA * 2 * 7 * 32];
__device__ __align__(128) float g_gate[SEQ];
__device__ unsigned g_cnt[32 * (1 + 2 * 16 + 8 + NCTA)];
constexpr int C_LAUNCH = 0, C_PREP = 32, C_Y = 32 * 17, C_W = 32 * 33, C_O = 32 * 41;

#define TSM(cond, slot) do { } while (0)
#define TSIF(cond, slot) do { if (__LINE__ >= FENCE_LO && __LINE__ < FENCE_HI) sched_fence(); } while (0)
__device__ __forceinline__ void sched_fence() {
  asm volatile("{\n.reg .pred p;\n.reg .u32 c;\nmov.u32 c, %%clock;\nsetp.eq.u32 p, c, 0;\n@p st.shared.u32 [%0], c;\n}"
               ::"r"(1024 + OFF_EPOCH + 4) : "memory");
}
#define TS(slot) TSIF(true, slot)

struct Params {
  const __nv_bfloat16 *q, *k, *v, *shift_k, *ssm_k, *ssm_D, *wqkv, *wo, *gate_w;
  __nv_bfloat16* out;
  uint32_t zero;
};

constexpr int SPIN_LIMIT = 1 << 17;

__device__ __forceinline__ void mbar_init(uint32_t bar, uint32_t count) {
  asm volatile("mbarrier.init.shared::cta.b64 [%0], %1;" ::"r"(bar), "r"(count) : "memory");
}
__device__ __forceinline__ void mbar_expect_tx(uint32_t bar, uint32_t bytes) {
  asm volatile("mbarrier.arrive.expect_tx.shared::cta.b64 _, [%0], %1;" ::"r"(bar), "r"(bytes) : "memory");
}
__device__ __forceinline__ void mbar_arrive(uint32_t bar) {
  asm volatile("mbarrier.arrive.shared::cta.b64 _, [%0];" ::"r"(bar) : "memory");
}
__device__ __forceinline__ void mbar_wait(uint32_t bar, uint32_t parity) {
  uint32_t ok;
  int spins = 0;
  do {
      asm volatile("{\n.reg .pred p;\nmbarrier.try_wait.parity.shared::cta.b64 p, [%1], %2;\nselp.b32 %0, 1, 0, p;\n}"
                   : "=r"(ok) : "r"(bar), "r"(parity) : "memory");
    if (++spins > SPIN_LIMIT) break;
  } while (!ok);
}
__device__ __forceinline__ unsigned flag_read(const unsigned* p) {
  unsigned v;
  asm volatile("ld.relaxed.gpu.global.u32 %0, [%1];" : "=r"(v) : "l"(p) : "memory");
  return v;
}
__device__ __forceinline__ void flag_poll(const unsigned* p, unsigned target) {
  unsigned v;
  int spins = 0;
  do {
    asm volatile("ld.relaxed.gpu.global.u32 %0, [%1];" : "=r"(v) : "l"(p) : "memory");
    if (++spins > SPIN_LIMIT) break;
  } while ((int)(v - target) < 0);
}
__device__ __forceinline__ void flag_wait(const unsigned* p, unsigned target) {
  flag_poll(p, target);
}
__device__ __forceinline__ void flag_signal(unsigned* p, int n, int lane) {
  if (lane == 0) asm volatile("fence.release.gpu;" ::: "memory");
  __syncwarp();
  if (lane < n) asm volatile("red.relaxed.gpu.global.add.u32 [%0], 1;" ::"l"(p + 32 * lane) : "memory");
}
__device__ __forceinline__ void flag_bump(unsigned* p) {
  asm volatile("red.relaxed.gpu.global.add.u32 [%0], 1;" ::"l"(p) : "memory");
}
__device__ __forceinline__ void fence_async_smem() { asm volatile("fence.proxy.async.shared::cta;" ::: "memory"); }
__device__ __forceinline__ void wg_sync(int id) { asm volatile("bar.sync %0, 128;" ::"r"(id) : "memory"); }

__device__ __forceinline__ void tma_2d(uint32_t dst, const CUtensorMap* tm, int c0, int c1, uint32_t bar) {
  asm volatile("cp.async.bulk.tensor.2d.shared::cluster.global.mbarrier::complete_tx::bytes [%0], [%1, {%3, %4}], [%2];"
               ::"r"(dst), "l"(tm), "r"(bar), "r"(c0), "r"(c1) : "memory");
}
__device__ __forceinline__ void tma_3d(uint32_t dst, const CUtensorMap* tm, int c0, int c1, int c2, uint32_t bar) {
  asm volatile("cp.async.bulk.tensor.3d.shared::cluster.global.mbarrier::complete_tx::bytes [%0], [%1, {%3, %4, %5}], [%2];"
               ::"r"(dst), "l"(tm), "r"(bar), "r"(c0), "r"(c1), "r"(c2) : "memory");
}
__device__ __forceinline__ void bulk_load(uint32_t dst, const void* src, uint32_t bytes, uint32_t bar) {
  asm volatile("cp.async.bulk.shared::cluster.global.mbarrier::complete_tx::bytes [%0], [%1], %2, [%3];"
               ::"r"(dst), "l"(src), "r"(bytes), "r"(bar) : "memory");
}
__device__ __forceinline__ void bulk_store(void* dst, uint32_t src, uint32_t bytes) {
  asm volatile("cp.async.bulk.global.shared::cta.bulk_group [%0], [%1], %2;" ::"l"(dst), "r"(src), "r"(bytes) : "memory");
}
__device__ __forceinline__ void bulk_wait_read() {
  asm volatile("cp.async.bulk.commit_group;\ncp.async.bulk.wait_group.read 0;" ::: "memory");
}

__device__ __forceinline__ void publish(void* dst, uint32_t src, uint32_t bytes) {
  bulk_store(dst, src, bytes);
  bulk_wait_read();
}

__device__ __forceinline__ void wg_fence() { asm volatile("wgmma.fence.sync.aligned;" ::: "memory"); }
__device__ __forceinline__ void wg_commit() { asm volatile("wgmma.commit_group.sync.aligned;" ::: "memory"); }
template <int N> __device__ __forceinline__ void wg_wait() { asm volatile("wgmma.wait_group.sync.aligned %0;" ::"n"(N) : "memory"); }
__device__ __forceinline__ uint32_t desc_lo(uint32_t addr, uint32_t lbo) { return ((addr & 0x3FFFF) >> 4) | ((lbo >> 4) << 16); }
constexpr uint32_t desc_hi(uint32_t sbo, uint32_t swz) { return (sbo >> 4) | (swz << 30); }
constexpr uint32_t HI_SW128 = desc_hi(1024, 1), HI_SW64 = desc_hi(512, 2), HI_SW32 = desc_hi(256, 3), HI_NONE = desc_hi(128, 0);
template <int N> __device__ __forceinline__ void pin(float* d) {
#pragma unroll
  for (int i = 0; i < N; i++) asm volatile("" : "+f"(d[i])::"memory");
}

__device__ __forceinline__ uint32_t lds32(uint32_t a) {
  uint32_t v;
  asm volatile("ld.volatile.shared.u32 %0, [%1];" : "=r"(v) : "r"(a) : "memory");
  return v;
}
__device__ __forceinline__ uint2 ldg64(const void* a) {
  uint2 v;
  asm volatile("ld.global.nc.v2.u32 {%0, %1}, [%2];" : "=r"(v.x), "=r"(v.y) : "l"(a) : "memory");
  return v;
}
__device__ __forceinline__ void ldsm4(uint32_t* r, uint32_t a) {
  asm volatile("ldmatrix.sync.aligned.m8n8.x4.shared.b16 {%0, %1, %2, %3}, [%4];"
               : "=r"(r[0]), "=r"(r[1]), "=r"(r[2]), "=r"(r[3]) : "r"(a) : "memory");
}
__device__ __forceinline__ void ldsm4t(uint32_t* r, uint32_t a) {
  asm volatile("ldmatrix.sync.aligned.m8n8.x4.trans.shared.b16 {%0, %1, %2, %3}, [%4];"
               : "=r"(r[0]), "=r"(r[1]), "=r"(r[2]), "=r"(r[3]) : "r"(a) : "memory");
}
__device__ __forceinline__ uint2 lds64(uint32_t a) {
  uint2 v;
  asm volatile("ld.shared.v2.u32 {%0, %1}, [%2];" : "=r"(v.x), "=r"(v.y) : "r"(a) : "memory");
  return v;
}
__device__ __forceinline__ uint4 lds128(uint32_t a) {
  uint4 v;
  asm volatile("ld.shared.v4.u32 {%0, %1, %2, %3}, [%4];" : "=r"(v.x), "=r"(v.y), "=r"(v.z), "=r"(v.w) : "r"(a) : "memory");
  return v;
}
__device__ __forceinline__ void sts128(uint32_t a, uint32_t x, uint32_t y, uint32_t z, uint32_t w) {
  asm volatile("st.shared.v4.u32 [%0], {%1, %2, %3, %4};" ::"r"(a), "r"(x), "r"(y), "r"(z), "r"(w) : "memory");
}
__device__ __forceinline__ void stsm4(uint32_t a, const uint32_t* r) {
  asm volatile("stmatrix.sync.aligned.m8n8.x4.shared.b16 [%0], {%1, %2, %3, %4};" ::"r"(a), "r"(r[0]), "r"(r[1]), "r"(r[2]), "r"(r[3]) : "memory");
}
__device__ __forceinline__ uint32_t pack2(float lo, float hi) {
  uint32_t r;
  asm("cvt.rn.bf16x2.f32 %0, %1, %2;" : "=r"(r) : "f"(hi), "f"(lo));
  return r;
}
__device__ __forceinline__ uint32_t movm(uint32_t a) {
  uint32_t d;
  asm volatile("movmatrix.sync.aligned.m8n8.trans.b16 %0, %1;" : "=r"(d) : "r"(a));
  return d;
}
__device__ __forceinline__ uint32_t bmul(uint32_t a, uint32_t b) {
  uint32_t d;
  asm("mul.rn.bf16x2 %0, %1, %2;" : "=r"(d) : "r"(a), "r"(b));
  return d;
}
__device__ __forceinline__ uint32_t badd(uint32_t a, uint32_t b) {
  uint32_t d;
  asm("add.rn.bf16x2 %0, %1, %2;" : "=r"(d) : "r"(a), "r"(b));
  return d;
}
__device__ __forceinline__ uint32_t bfma(uint32_t a, uint32_t b, uint32_t c) {
  uint32_t d;
  asm("fma.rn.bf16x2 %0, %1, %2, %3;" : "=r"(d) : "r"(a), "r"(b), "r"(c));
  return d;
}
__device__ __forceinline__ float bf_lo(uint32_t x) { return __uint_as_float(x << 16); }
__device__ __forceinline__ float bf_hi(uint32_t x) { return __uint_as_float(x & 0xFFFF0000u); }
__device__ __forceinline__ float ex2(float x) {
  float y;
  asm("ex2.approx.ftz.f32 %0, %1;" : "=f"(y) : "f"(x));
  return y;
}
__device__ __forceinline__ float rcp(float x) {
  float y;
  asm("rcp.approx.ftz.f32 %0, %1;" : "=f"(y) : "f"(x));
  return y;
}
__device__ __forceinline__ void mma16816(float* d, uint32_t a0, uint32_t a1, uint32_t a2, uint32_t a3, uint32_t b0, uint32_t b1) {
  asm volatile("mma.sync.aligned.m16n8k16.row.col.f32.bf16.bf16.f32 {%0, %1, %2, %3}, {%4, %5, %6, %7}, {%8, %9}, {%0, %1, %2, %3};"
               : "+f"(d[0]), "+f"(d[1]), "+f"(d[2]), "+f"(d[3])
               : "r"(a0), "r"(a1), "r"(a2), "r"(a3), "r"(b0), "r"(b1));
}
__device__ __forceinline__ void mma1688(float* d, uint32_t a0, uint32_t a1, uint32_t b0) {
  asm volatile("mma.sync.aligned.m16n8k8.row.col.f32.bf16.bf16.f32 {%0, %1, %2, %3}, {%4, %5}, {%6}, {%0, %1, %2, %3};"
               : "+f"(d[0]), "+f"(d[1]), "+f"(d[2]), "+f"(d[3])
               : "r"(a0), "r"(a1), "r"(b0));
}

template <int N> struct WgRS;
template <int N> struct WgSST;
template <> struct WgRS<32> {
  template <uint32_t HB>
  static __device__ __forceinline__ void mma(float* d, const uint32_t* a, uint32_t db) {
    asm volatile("{\n.reg .pred p;\n.reg .b64 db;\nsetp.ne.b32 p, %22, 0;\n"
      "mov.b64 db, {%20, %21};\n"
      "wgmma.mma_async.sync.aligned.m64n32k16.f32.bf16.bf16 {"
      "%0, %1, %2, %3, %4, %5, %6, %7, %8, %9, %10, %11, %12, %13, %14, %15"
      "}, {%16, %17, %18, %19}, db, p, 1, 1, 1;\n}\n"
      : "+f"(d[0]), "+f"(d[1]), "+f"(d[2]), "+f"(d[3]), "+f"(d[4]), "+f"(d[5]), "+f"(d[6]), "+f"(d[7]),
        "+f"(d[8]), "+f"(d[9]), "+f"(d[10]), "+f"(d[11]), "+f"(d[12]), "+f"(d[13]), "+f"(d[14]), "+f"(d[15])
      : "r"(a[0]), "r"(a[1]), "r"(a[2]), "r"(a[3]), "r"(db), "n"(HB), "n"(1));
  }
  template <uint32_t HB>
  static __device__ __forceinline__ void set(float* d, const uint32_t* a, uint32_t db) {
    asm volatile("{\n.reg .pred p;\n.reg .b64 db;\nsetp.ne.b32 p, %22, 0;\n"
      "mov.b64 db, {%20, %21};\n"
      "wgmma.mma_async.sync.aligned.m64n32k16.f32.bf16.bf16 {"
      "%0, %1, %2, %3, %4, %5, %6, %7, %8, %9, %10, %11, %12, %13, %14, %15"
      "}, {%16, %17, %18, %19}, db, p, 1, 1, 1;\n}\n"
      : "=f"(d[0]), "=f"(d[1]), "=f"(d[2]), "=f"(d[3]), "=f"(d[4]), "=f"(d[5]), "=f"(d[6]), "=f"(d[7]),
        "=f"(d[8]), "=f"(d[9]), "=f"(d[10]), "=f"(d[11]), "=f"(d[12]), "=f"(d[13]), "=f"(d[14]), "=f"(d[15])
      : "r"(a[0]), "r"(a[1]), "r"(a[2]), "r"(a[3]), "r"(db), "n"(HB), "n"(0));
  }
};
template <> struct WgRS<64> {
  template <uint32_t HB>
  static __device__ __forceinline__ void mma(float* d, const uint32_t* a, uint32_t db) {
    asm volatile("{\n.reg .pred p;\n.reg .b64 db;\nsetp.ne.b32 p, %38, 0;\n"
      "mov.b64 db, {%36, %37};\n"
      "wgmma.mma_async.sync.aligned.m64n64k16.f32.bf16.bf16 {"
      "%0, %1, %2, %3, %4, %5, %6, %7, %8, %9, %10, %11, %12, %13, %14, %15, "
      "%16, %17, %18, %19, %20, %21, %22, %23, %24, %25, %26, %27, %28, %29, %30, %31"
      "}, {%32, %33, %34, %35}, db, p, 1, 1, 1;\n}\n"
      : "+f"(d[0]), "+f"(d[1]), "+f"(d[2]), "+f"(d[3]), "+f"(d[4]), "+f"(d[5]), "+f"(d[6]), "+f"(d[7]),
        "+f"(d[8]), "+f"(d[9]), "+f"(d[10]), "+f"(d[11]), "+f"(d[12]), "+f"(d[13]), "+f"(d[14]), "+f"(d[15]),
        "+f"(d[16]), "+f"(d[17]), "+f"(d[18]), "+f"(d[19]), "+f"(d[20]), "+f"(d[21]), "+f"(d[22]), "+f"(d[23]),
        "+f"(d[24]), "+f"(d[25]), "+f"(d[26]), "+f"(d[27]), "+f"(d[28]), "+f"(d[29]), "+f"(d[30]), "+f"(d[31])
      : "r"(a[0]), "r"(a[1]), "r"(a[2]), "r"(a[3]), "r"(db), "n"(HB), "n"(1));
  }
  template <uint32_t HB>
  static __device__ __forceinline__ void set(float* d, const uint32_t* a, uint32_t db) {
    asm volatile("{\n.reg .pred p;\n.reg .b64 db;\nsetp.ne.b32 p, %38, 0;\n"
      "mov.b64 db, {%36, %37};\n"
      "wgmma.mma_async.sync.aligned.m64n64k16.f32.bf16.bf16 {"
      "%0, %1, %2, %3, %4, %5, %6, %7, %8, %9, %10, %11, %12, %13, %14, %15, "
      "%16, %17, %18, %19, %20, %21, %22, %23, %24, %25, %26, %27, %28, %29, %30, %31"
      "}, {%32, %33, %34, %35}, db, p, 1, 1, 1;\n}\n"
      : "=f"(d[0]), "=f"(d[1]), "=f"(d[2]), "=f"(d[3]), "=f"(d[4]), "=f"(d[5]), "=f"(d[6]), "=f"(d[7]),
        "=f"(d[8]), "=f"(d[9]), "=f"(d[10]), "=f"(d[11]), "=f"(d[12]), "=f"(d[13]), "=f"(d[14]), "=f"(d[15]),
        "=f"(d[16]), "=f"(d[17]), "=f"(d[18]), "=f"(d[19]), "=f"(d[20]), "=f"(d[21]), "=f"(d[22]), "=f"(d[23]),
        "=f"(d[24]), "=f"(d[25]), "=f"(d[26]), "=f"(d[27]), "=f"(d[28]), "=f"(d[29]), "=f"(d[30]), "=f"(d[31])
      : "r"(a[0]), "r"(a[1]), "r"(a[2]), "r"(a[3]), "r"(db), "n"(HB), "n"(0));
  }
};
template <> struct WgSST<48> {
  template <uint32_t HA, uint32_t HB>
  static __device__ __forceinline__ void mma(float* d, uint32_t da, uint32_t db, int sc) {
    asm volatile("{\n.reg .pred p;\n.reg .b64 da, db;\nsetp.ne.b32 p, %28, 0;\n"
      "mov.b64 da, {%24, %25};\nmov.b64 db, {%26, %27};\n"
      "wgmma.mma_async.sync.aligned.m64n48k16.f32.bf16.bf16 {"
      "%0, %1, %2, %3, %4, %5, %6, %7, %8, %9, %10, %11, %12, %13, %14, %15, "
      "%16, %17, %18, %19, %20, %21, %22, %23"
      "}, da, db, p, 1, 1, 0, 1;\n}\n"
      : "+f"(d[0]), "+f"(d[1]), "+f"(d[2]), "+f"(d[3]), "+f"(d[4]), "+f"(d[5]), "+f"(d[6]), "+f"(d[7]),
        "+f"(d[8]), "+f"(d[9]), "+f"(d[10]), "+f"(d[11]), "+f"(d[12]), "+f"(d[13]), "+f"(d[14]), "+f"(d[15]),
        "+f"(d[16]), "+f"(d[17]), "+f"(d[18]), "+f"(d[19]), "+f"(d[20]), "+f"(d[21]), "+f"(d[22]), "+f"(d[23])
      : "r"(da), "n"(HA), "r"(db), "n"(HB), "r"(sc));
  }
};
template <> struct WgSST<80> {
  template <uint32_t HA, uint32_t HB>
  static __device__ __forceinline__ void mma(float* d, uint32_t da, uint32_t db, int sc) {
    asm volatile("{\n.reg .pred p;\n.reg .b64 da, db;\nsetp.ne.b32 p, %44, 0;\n"
      "mov.b64 da, {%40, %41};\nmov.b64 db, {%42, %43};\n"
      "wgmma.mma_async.sync.aligned.m64n80k16.f32.bf16.bf16 {"
      "%0, %1, %2, %3, %4, %5, %6, %7, %8, %9, %10, %11, %12, %13, %14, %15, "
      "%16, %17, %18, %19, %20, %21, %22, %23, %24, %25, %26, %27, %28, %29, %30, %31, "
      "%32, %33, %34, %35, %36, %37, %38, %39"
      "}, da, db, p, 1, 1, 0, 1;\n}\n"
      : "+f"(d[0]), "+f"(d[1]), "+f"(d[2]), "+f"(d[3]), "+f"(d[4]), "+f"(d[5]), "+f"(d[6]), "+f"(d[7]),
        "+f"(d[8]), "+f"(d[9]), "+f"(d[10]), "+f"(d[11]), "+f"(d[12]), "+f"(d[13]), "+f"(d[14]), "+f"(d[15]),
        "+f"(d[16]), "+f"(d[17]), "+f"(d[18]), "+f"(d[19]), "+f"(d[20]), "+f"(d[21]), "+f"(d[22]), "+f"(d[23]),
        "+f"(d[24]), "+f"(d[25]), "+f"(d[26]), "+f"(d[27]), "+f"(d[28]), "+f"(d[29]), "+f"(d[30]), "+f"(d[31]),
        "+f"(d[32]), "+f"(d[33]), "+f"(d[34]), "+f"(d[35]), "+f"(d[36]), "+f"(d[37]), "+f"(d[38]), "+f"(d[39])
      : "r"(da), "n"(HA), "r"(db), "n"(HB), "r"(sc));
  }
};
template <> struct WgSST<192> {
  template <uint32_t HA, uint32_t HB>
  static __device__ __forceinline__ void mma(float* d, uint32_t da, uint32_t db, int sc) {
    asm volatile("{\n.reg .pred p;\n.reg .b64 da, db;\nsetp.ne.b32 p, %100, 0;\n"
      "mov.b64 da, {%96, %97};\nmov.b64 db, {%98, %99};\n"
      "wgmma.mma_async.sync.aligned.m64n192k16.f32.bf16.bf16 {"
      "%0, %1, %2, %3, %4, %5, %6, %7, %8, %9, %10, %11, %12, %13, %14, %15, "
      "%16, %17, %18, %19, %20, %21, %22, %23, %24, %25, %26, %27, %28, %29, %30, %31, "
      "%32, %33, %34, %35, %36, %37, %38, %39, %40, %41, %42, %43, %44, %45, %46, %47, "
      "%48, %49, %50, %51, %52, %53, %54, %55, %56, %57, %58, %59, %60, %61, %62, %63, "
      "%64, %65, %66, %67, %68, %69, %70, %71, %72, %73, %74, %75, %76, %77, %78, %79, "
      "%80, %81, %82, %83, %84, %85, %86, %87, %88, %89, %90, %91, %92, %93, %94, %95"
      "}, da, db, p, 1, 1, 0, 1;\n}\n"
      : "+f"(d[0]), "+f"(d[1]), "+f"(d[2]), "+f"(d[3]), "+f"(d[4]), "+f"(d[5]), "+f"(d[6]), "+f"(d[7]),
        "+f"(d[8]), "+f"(d[9]), "+f"(d[10]), "+f"(d[11]), "+f"(d[12]), "+f"(d[13]), "+f"(d[14]), "+f"(d[15]),
        "+f"(d[16]), "+f"(d[17]), "+f"(d[18]), "+f"(d[19]), "+f"(d[20]), "+f"(d[21]), "+f"(d[22]), "+f"(d[23]),
        "+f"(d[24]), "+f"(d[25]), "+f"(d[26]), "+f"(d[27]), "+f"(d[28]), "+f"(d[29]), "+f"(d[30]), "+f"(d[31]),
        "+f"(d[32]), "+f"(d[33]), "+f"(d[34]), "+f"(d[35]), "+f"(d[36]), "+f"(d[37]), "+f"(d[38]), "+f"(d[39]),
        "+f"(d[40]), "+f"(d[41]), "+f"(d[42]), "+f"(d[43]), "+f"(d[44]), "+f"(d[45]), "+f"(d[46]), "+f"(d[47]),
        "+f"(d[48]), "+f"(d[49]), "+f"(d[50]), "+f"(d[51]), "+f"(d[52]), "+f"(d[53]), "+f"(d[54]), "+f"(d[55]),
        "+f"(d[56]), "+f"(d[57]), "+f"(d[58]), "+f"(d[59]), "+f"(d[60]), "+f"(d[61]), "+f"(d[62]), "+f"(d[63]),
        "+f"(d[64]), "+f"(d[65]), "+f"(d[66]), "+f"(d[67]), "+f"(d[68]), "+f"(d[69]), "+f"(d[70]), "+f"(d[71]),
        "+f"(d[72]), "+f"(d[73]), "+f"(d[74]), "+f"(d[75]), "+f"(d[76]), "+f"(d[77]), "+f"(d[78]), "+f"(d[79]),
        "+f"(d[80]), "+f"(d[81]), "+f"(d[82]), "+f"(d[83]), "+f"(d[84]), "+f"(d[85]), "+f"(d[86]), "+f"(d[87]),
        "+f"(d[88]), "+f"(d[89]), "+f"(d[90]), "+f"(d[91]), "+f"(d[92]), "+f"(d[93]), "+f"(d[94]), "+f"(d[95])
      : "r"(da), "n"(HA), "r"(db), "n"(HB), "r"(sc));
  }
};

struct FftConst {
  uint32_t f[2][4], fi[4][4];
  uint32_t ta[2][2], tb[2][2];
};
__device__ __forceinline__ void cis(int m, float scale, float& c, float& s) {
  const float a = (float)m * (-6.283185307179586f * scale);
  c = __cosf(a);
  s = __sinf(a);
}
__device__ __forceinline__ void fft_tables(uint32_t (&v)[12], int tw) {
  const int row = tw >> 2, ch = tw & 3;
#pragma unroll
  for (int i = 0; i < 4; i++) {
    float c[2], s[2], x[2];
#pragma unroll
    for (int e = 0; e < 2; e++) {
      cis((((32 * (8 * ch + 2 * i + e) + 15) * (4 * row - 63) + 2048) & 4095) - 2048, 1.f / 4096, c[e], s[e]);
      float gc, gs;
      cis((((row & 15) * (8 * (ch & 1) + 2 * i + e) + 8) & 15) - 8, 1.f / 16, gc, gs);
      x[e] = (row >> 4) == (ch >> 1) ? gc : (ch >> 1) ? gs : -gs;
    }
    v[i] = pack2(c[0] * 0.125f, c[1] * 0.125f);
    v[4 + i] = pack2(s[0] * 0.125f, s[1] * 0.125f);
    v[8 + i] = pack2(x[0], x[1]);
  }
#pragma unroll
  for (int i = 0; i < 12; i++) asm volatile("" : "+r"(v[i]));
}
__device__ __forceinline__ void fft_tables_store(const uint32_t (&v)[12], uint32_t sb, int tw) {
  const int row = tw >> 2;
  const uint32_t x = ((tw ^ (row >> 1)) & 3) << 4, a = sb + OFF_FT + (16 * (row >> 3) + (row & 7)) * 64 + x;
  sts128(a, v[0], v[1], v[2], v[3]);
  sts128(a + 512, v[4], v[5], v[6], v[7]);
  sts128(sb + OFF_GT + row * 64 + x, v[8], v[9], v[10], v[11]);
}
__device__ __forceinline__ void fft_twiddles(uint32_t (&v)[2], int tw) {
  float a[2], s[2];
#pragma unroll
  for (int i = 0; i < 2; i++) {
    float c;
    cis((2 * (2 * (tw & 3) + i) - 15) * (4 * (tw >> 2) - 63), 1.f / 4096, c, s[i]);
    a[i] = __fdividef(-s[i], 1.f + c);
  }
  v[0] = pack2(a[0], a[1]);
  v[1] = pack2(s[0], s[1]);
  asm volatile("" : "+r"(v[0]), "+r"(v[1]));
}
__device__ __forceinline__ void fft_matrices(FftConst& k, uint32_t sb, int w, int lane) {
  const uint32_t x = (lane >> 1) & 3;
  const uint2 t0 = lds64(sb + OFF_TT + 256 * w + 8 * lane), t1 = lds64(sb + OFF_TT + 256 * w + 8 * (lane ^ 3));
  k.ta[0][0] = t0.x;
  k.tb[0][0] = t0.y;
  k.ta[1][1] = __byte_perm(t1.x, 0, 0x1032);
  k.tb[1][1] = __byte_perm(t1.y, 0, 0x1032);
#pragma unroll
  for (int j = 0; j < 2; j++) {
    k.ta[1 - j][j] = k.ta[j][j] ^ 0x80008000u;
    k.tb[1 - j][j] = k.tb[j][j] ^ 0x80008000u;
    asm volatile("" : "+r"(k.ta[0][j]), "+r"(k.tb[0][j]), "+r"(k.ta[1][j]), "+r"(k.tb[1][j]));
  }
#pragma unroll
  for (int i = 0; i < 2; i++) {
    ldsm4(k.f[i], sb + OFF_FT + (16 * w + (lane & 15)) * 64 + (((2 * i + (lane >> 4)) ^ x) << 4));
    ldsm4t(k.fi[i], sb + OFF_FT + (32 * i + lane) * 64 + ((w ^ x) << 4));
#pragma unroll
    for (int j = 0; j < 4; j++) {
      k.fi[2 + i][j] = (j & 1) ? k.fi[i][j - 1] ^ 0x80008000u : k.fi[i][j + 1];
      asm volatile("" : "+r"(k.fi[2 + i][j]));
    }
  }
}
__device__ __forceinline__ void rot(uint32_t& x, uint32_t& y, uint32_t a, uint32_t b) {
  x = bfma(a, y, x);
  y = bfma(b, x, y);
  x = bfma(a, y, x);
}
__device__ __forceinline__ void twiddle_fwd(uint32_t (&a)[4][4], float* d, const FftConst& k) {
#pragma unroll
  for (int q = 0; q < 4; q++)
#pragma unroll
    for (int j = 0; j < 2; j++) {
      const float* x = d + 8 * q + 4 * j;
      uint32_t re = pack2(x[0], x[1]), im = pack2(x[2], x[3]);
      rot(re, im, k.ta[0][j], k.tb[0][j]);
      a[q & 2][2 * j + (q & 1)] = re;
      a[(q & 2) + 1][2 * j + (q & 1)] = im;
    }
}
__device__ __forceinline__ void g_step(float* d, const uint32_t (&a)[4][4], uint32_t dre, uint32_t dim) {
  WgRS<32>::set<HI_SW64>(d, a[0], dre);
  WgRS<32>::set<HI_SW64>(d + 16, a[2], dre);
  WgRS<32>::mma<HI_SW64>(d, a[1], dim);
  WgRS<32>::mma<HI_SW64>(d + 16, a[3], dim);
  wg_commit();
}

__device__ __forceinline__ void products(uint32_t (&a)[4][4], const float* H, const float* U, int p) {
#pragma unroll
  for (int j = 0; j < 2; j++)
#pragma unroll
    for (int m = 2 * p; m < 2 * p + 2; m++) {
      float pr[2], pi[2];
#pragma unroll
      for (int x = 0; x < 2; x++)
#pragma unroll
        for (int q = 0; q <= m; q++) {
          const int ih = 16 * (q >> 1) + 2 * (q & 1) + 4 * j + x, iu = 16 * ((m - q) >> 1) + 2 * ((m - q) & 1) + 4 * j + x;
          pr[x] = q ? fmaf(H[ih], U[iu], pr[x]) : H[ih] * U[iu];
          pi[x] = q ? fmaf(H[ih], U[iu + 8], pi[x]) : H[ih] * U[iu + 8];
          pr[x] = fmaf(-H[ih + 8], U[iu + 8], pr[x]);
          pi[x] = fmaf(H[ih + 8], U[iu], pi[x]);
        }
      a[m & 2][2 * j + (m & 1)] = pack2(pr[0], pr[1]);
      a[(m & 2) + 1][2 * j + (m & 1)] = pack2(pi[0], pi[1]);
    }
}

__device__ __forceinline__ void conv_channel(const FftConst& k, uint32_t sb, int c, int wg, int w, int lane) {
  const uint32_t cb = sb + off_ch(c), bars = sb + OFF_BAR;
  const uint32_t du = desc_lo(cb, 1024), dg = desc_lo(sb + OFF_GT, 16), dz = desc_lo(cb + U_BYTES, 16);
  float U[32], H[32];
  uint32_t a[4][4], e[4][4];
  const float dv = __uint_as_float(lds32(sb + OFF_D + 4 * c));
  wg_fence();
  WgRS<64>::set<HI_SW32>(H, k.f[0], du + 256);
  WgRS<64>::mma<HI_SW32>(H, k.f[1], du + 256 + 32);
  wg_commit();
  wg_wait<0>();
  pin<32>(H);
  twiddle_fwd(a, H, k);
  mbar_wait(bars + 8 * (B_U + (c < 3 ? c : 3)), 0);
  TSM(w == 0 && c < 3, 7 + wg);
  wg_fence();
  WgRS<64>::set<HI_SW32>(U, k.f[0], du);
  WgRS<64>::mma<HI_SW32>(U, k.f[1], du + 32);
  wg_commit();
  g_step(H, a, dg, dg + 64);
  wg_wait<1>();
  pin<32>(U);
  twiddle_fwd(e, U, k);
  wg_fence();
  g_step(U, e, dg, dg + 64);
  wg_wait<0>();
  pin<32>(U);
  pin<32>(H);
#pragma unroll
  for (int j = 0; j < 4; j++) H[4 * (j >> 1) + (j & 1)] += dv;
  float V[32];
#pragma unroll
  for (int p = 0; p < 2; p++) {
    products(a, H, U, p);
    wg_fence();
    WgRS<32>::set<HI_SW64>(V + 16 * p, a[2 * p], dg + 64);
    WgRS<32>::mma<HI_SW64>(V + 16 * p, a[2 * p + 1], dg);
    wg_commit();
  }
  const uint32_t za = cb + U_BYTES + (8 * w + (lane & 7)) * 128 + (((lane >> 3) ^ (lane & 7)) << 4);
  const uint32_t ya = cb + (lane >> 4) * 1024 + (8 * w + (lane & 7)) * 32 + ((((lane >> 3) ^ (lane >> 2)) & 1) << 4);
  wg_sync(1 + wg);
#pragma unroll
  for (int p = 0; p < 2; p++) {
    if (p == 0) wg_wait<1>();
    else wg_wait<0>();
    pin<16>(V + 16 * p);
#pragma unroll
    for (int i = 0; i < 4; i++) {
      const int j = i & 1;
      const float* x = V + 16 * p + 4 * j + (i & 2);
      e[p][i] = pack2(x[8], x[9]);
      e[2 + p][i] = pack2(x[0], x[1]);
      rot(e[p][i], e[2 + p][i], k.ta[1][j], k.tb[1][j]);
    }
    stsm4(za ^ (64 * p), e[p]);
    stsm4((za ^ (64 * p)) + 4096, e[2 + p]);
  }
  fence_async_smem();
  wg_sync(1 + wg);
  wg_fence();
  WgRS<64>::set<HI_SW128>(H, k.fi[0], dz);
#pragma unroll
  for (int ks = 1; ks < 4; ks++) WgRS<64>::mma<HI_SW128>(H, k.fi[ks], dz + 128 * ks);
  wg_commit();
  wg_wait<0>();
  pin<32>(H);
  if (lane == 0) mbar_arrive(bars + 8 * B_CVD);
  TSIF(w == 0, 88 + c);
#pragma unroll
  for (int j = 0; j < 8; j++)
    a[j >> 2][j & 3] = j < 2 ? pack2(H[4 * j], H[4 * j + 1]) : pack2(H[4 * j] + H[4 * j - 6], H[4 * j + 1] + H[4 * j - 5]);
  stsm4(ya, a[0]);
  stsm4(ya + 2048, a[1]);
  fence_async_smem();
  __syncwarp();
}

__device__ __forceinline__ void prep_slab(uint4* res, const uint2* sw, uint32_t sb, int slab, int w, int lane) {
  const int t = lane & 3, tp = (lane & 7) >> 1, pos = 8 * tp + 2 * (((lane >> 3) + tp) & 3) + (lane & 1);
  const uint32_t base = sb + OFF_KVS + slab * KVS_BYTES + pos * 128;
  uint32_t kk[2][4][4], vv[2][4];
  mbar_wait(sb + OFF_BAR + 8 * (B_KV + slab), 0);
#pragma unroll
  for (int h = 0; h < 2; h++) {
#pragma unroll
    for (int j = 0; j < 4; j++) {
      const uint32_t a = base + 128 * j;
      ldsm4t(kk[h][j], a + (((w + 4 * h) ^ ((a >> 7) & 7)) << 4));
    }
    const uint32_t a = base + KVS_V;
    ldsm4t(vv[h], a + (((w + 4 * h) ^ ((a >> 7) & 7)) << 4));
  }
#pragma unroll
  for (int h = 0; h < 2; h++) {
    uint32_t (&k)[4][4] = kk[h];
    uint32_t (&v)[4] = vv[h];
    const uint32_t w0 = __byte_perm(sw[h].x, 0, 0x1010), w1 = __byte_perm(sw[h].x, 0, 0x3232);
    const uint32_t w2 = __byte_perm(sw[h].y, 0, 0x1010), w3 = __byte_perm(sw[h].y, 0, 0x3232);
#pragma unroll
    for (int m = 0; m < 4; m++)
      v[m] = bmul(badd(badd(badd(bmul(k[0][m], w3), bmul(k[1][m], w2)), bmul(k[2][m], w1)), bmul(k[3][m], w0)), v[m]);
    uint32_t a[4];
#pragma unroll
    for (int m = 0; m < 4; m++) a[m] = (t & 1) ? v[(m + 3) & 3] : v[m];
    res[h] = (t & 2) ? make_uint4(a[2], a[3], a[0], a[1]) : make_uint4(a[0], a[1], a[2], a[3]);
  }
}

__device__ __forceinline__ void prep_gate(const Params& p, uint32_t sb, int b, int w, int lane) {
  uint2 gw[5], x[4][5];
#pragma unroll
  for (int j = 0; j < 5; j++) gw[j] = ldg64(reinterpret_cast<const uint2*>(p.gate_w) + lane + 32 * j);
#pragma unroll
  for (int i = 0; i < 4; i++)
#pragma unroll
    for (int j = 0; j < 5; j++)
      x[i][j] = ldg64(reinterpret_cast<const uint2*>(p.q) + (16 * b + 4 * w + i) * (DIM / 4) + lane + 32 * j);
  float s[4];
#pragma unroll
  for (int i = 0; i < 4; i++) {
    s[i] = 0.f;
#pragma unroll
    for (int j = 0; j < 5; j++) {
      const uint32_t m0 = bmul(x[i][j].x, gw[j].x), m1 = bmul(x[i][j].y, gw[j].y);
      s[i] += (bf_lo(m0) + bf_hi(m0)) + (bf_lo(m1) + bf_hi(m1));
    }
  }
  const bool h = lane & 16, q = lane & 8;
  const float a = (h ? s[2] : s[0]) + __shfl_xor_sync(0xffffffffu, h ? s[0] : s[2], 16);
  const float c = (h ? s[3] : s[1]) + __shfl_xor_sync(0xffffffffu, h ? s[1] : s[3], 16);
  float z = (q ? c : a) + __shfl_xor_sync(0xffffffffu, q ? a : c, 8);
#pragma unroll
  for (int o = 4; o > 0; o >>= 1) z += __shfl_xor_sync(0xffffffffu, z, o);
  z = bf_lo(pack2(z, 0.f));
  z = bf_lo(pack2(__fdividef(1.f, 1.f + __expf(-z)), 0.f));
  mbar_wait(sb + OFF_BAR + 8 * B_S3, 0);
  if ((lane & 7) == 0) asm volatile("st.shared.f32 [%0], %1;" ::"r"(sb + OFF_GATE + 64 * (b & 7) + 16 * w + (lane >> 1)), "f"(z) : "memory");
  fence_async_smem();
}

__device__ __forceinline__ uint32_t bmax(uint32_t a, uint32_t b) {
  uint32_t d;
  asm("max.bf16x2 %0, %1, %2;" : "=r"(d) : "r"(a), "r"(b));
  return d;
}
__device__ __forceinline__ void softmax_two(const float (&l)[2][2], uint32_t& p0, uint32_t& p1) {
  constexpr float kScale = 0.22360679774997896f, kLog2e = 1.4426950408889634f;
  const uint32_t r0 = pack2(l[0][0], l[1][0]), r1 = pack2(l[0][1], l[1][1]);
  const uint32_t x0 = pack2(bf_lo(r0) * kScale, bf_hi(r0) * kScale), x1 = pack2(bf_lo(r1) * kScale, bf_hi(r1) * kScale);
  uint32_t m = bmax(x0, x1);
  m = bmax(m, __shfl_xor_sync(0xffffffffu, m, 1));
  m = bmax(m, __shfl_xor_sync(0xffffffffu, m, 2));
  const float m0 = bf_lo(m) * kLog2e, m1 = bf_hi(m) * kLog2e;
  p0 = pack2(ex2(bf_lo(x0) * kLog2e - m0), ex2(bf_lo(x1) * kLog2e - m0));
  p1 = pack2(ex2(bf_hi(x0) * kLog2e - m1), ex2(bf_hi(x1) * kLog2e - m1));
}

__device__ __forceinline__ void halo_read(uint32_t (&kpv)[10], uint32_t (&vpv)[10], uint32_t (&tg)[7], const uint4* hp) {
#pragma unroll
  for (int j = 0; j < 7; j++) {
    uint32_t x0, x1, x2;
    asm volatile("ld.relaxed.gpu.global.v4.u32 {%0, %1, %2, %3}, [%4];"
                 : "=r"(x0), "=r"(x1), "=r"(x2), "=r"(tg[j]) : "l"(hp + 32 * j) : "memory");
    if (j < 4) kpv[3 * j] = x0; else vpv[3 * j - 10] = x0;
    if (j < 3) kpv[3 * j + 1] = x1; else vpv[3 * j - 9] = x1;
    if (j < 3) kpv[3 * j + 2] = x2; else if (j < 6) vpv[3 * j - 8] = x2;
  }
}

template <int ROT>
__device__ __forceinline__ void pack_qkv(const float* acc, uint32_t (&qlo)[10], uint32_t (&qhi)[10], uint32_t (&klo)[10],
                                         uint32_t (&khi)[10], uint32_t (&vlo)[10], uint32_t (&vhi)[10]) {
#pragma unroll
  for (int j = 0; j < 10; j++) {
    const int x = (j + ROT) % 10, tq = x < 8 ? x : 16 + x, tk = x < 8 ? 8 + x : 18 + x, tv = x < 8 ? 16 + x : 20 + x;
    khi[j] = pack2(acc[4 * tk + 2], acc[4 * tk + 3]);
    vhi[j] = movm(pack2(acc[4 * tv + 2], acc[4 * tv + 3]));
    qlo[j] = pack2(acc[4 * tq], acc[4 * tq + 1]);
    qhi[j] = pack2(acc[4 * tq + 2], acc[4 * tq + 3]);
    klo[j] = pack2(acc[4 * tk], acc[4 * tk + 1]);
    vlo[j] = pack2(acc[4 * tv], acc[4 * tv + 1]);
    asm volatile("" : "+r"(khi[j]), "+r"(qlo[j]), "+r"(qhi[j]), "+r"(klo[j]), "+r"(vlo[j]));
  }
}

template <int ROT> __device__ __forceinline__ void halo_send(const float* acc, uint4* ho, uint32_t tag) {
#pragma unroll
  for (int j = 0; j < 7; j++) {
    uint32_t x[3];
#pragma unroll
    for (int e = 0; e < 3; e++) {
      const int i = 3 * j + e, y = (i % 10 + ROT) % 10, tk = y < 8 ? 8 + y : 18 + y, tv = y < 8 ? 16 + y : 20 + y;
      x[e] = i < 10 ? pack2(acc[4 * tk + 2], acc[4 * tk + 3]) : i < 20 ? movm(pack2(acc[4 * tv + 2], acc[4 * tv + 3])) : 0u;
    }
    asm volatile("st.relaxed.gpu.global.v4.u32 [%0], {%1, %2, %3, %4};" ::"l"(ho + 32 * j), "r"(x[0]), "r"(x[1]), "r"(x[2]), "r"(tag) : "memory");
  }
}

__device__ __forceinline__ void attention(float* acc, uint32_t sb, int b, int par, int w, int lane, uint32_t tag) {
  const int g = lane >> 2, t = lane & 3;
  uint32_t klo[10], khi[10], vlo[10], vhi[10], qlo[10], qhi[10], kpv[10], vpv[10];
  if (w == 3 && b < NCTA - 8) {
    uint4* ho = g_halo + (b * 2 + par) * 224 + lane;
    if (tail_first(b & 7)) halo_send<8>(acc, ho, tag);
    else halo_send<0>(acc, ho, tag);
    TSIF(par == 0, 76);
    pin<120>(acc);
  }
  if (tail_first(b & 7)) pack_qkv<8>(acc, qlo, qhi, klo, khi, vlo, vhi);
  else pack_qkv<0>(acc, qlo, qhi, klo, khi, vlo, vhi);
  const uint32_t xa = sb + OFF_KVX + (par * 3) * 2560 + lane * 16;
  if (w < 3) {
    sts128(xa + w * 2560, khi[0], khi[1], khi[2], khi[3]);
    sts128(xa + w * 2560 + 512, khi[4], khi[5], khi[6], khi[7]);
    sts128(xa + w * 2560 + 1024, khi[8], khi[9], vhi[0], vhi[1]);
    sts128(xa + w * 2560 + 1536, vhi[2], vhi[3], vhi[4], vhi[5]);
    sts128(xa + w * 2560 + 2048, vhi[6], vhi[7], vhi[8], vhi[9]);
  }
  TSIF(par == 0 && w == 1, 64);
#pragma unroll
  for (int j = 0; j < 10; j++) vlo[j] = movm(vlo[j]);
  const bool far0 = 2 * t > g, far1 = 2 * t + 1 > g;
  const uint32_t mfar = (far0 ? 0x0000FFFFu : 0u) | (far1 ? 0xFFFF0000u : 0u);
  float slo[4][2], lg[2][2];
  uint32_t phi[4], plo[4], qml[4], qmh[4];
#pragma unroll
  for (int h = 0; h < 4; h++) {
    const int f = h == 0 ? 0 : h == 1 ? 3 : h == 2 ? 5 : 8, hf = h < 2 ? 2 : 7;
    const bool mine = (h & 1) ? t >= 2 : t < 2;
    qml[h] = mine ? qlo[hf] : 0u;
    qmh[h] = mine ? qhi[hf] : 0u;
    float a[4] = {0.f, 0.f, 0.f, 0.f}, c[4] = {0.f, 0.f, 0.f, 0.f};
    mma16816(a, qlo[f], qhi[f], qlo[f + 1], qhi[f + 1], klo[f], klo[f + 1]);
    mma16816(c, qlo[f], qhi[f], qlo[f + 1], qhi[f + 1], khi[f], khi[f + 1]);
    mma1688(a, qml[h], qmh[h], klo[hf]);
    mma1688(c, qml[h], qmh[h], khi[hf]);
    slo[h][0] = a[0];
    slo[h][1] = a[1];
    lg[h & 1][0] = far0 ? a[2] : c[2];
    lg[h & 1][1] = far1 ? a[3] : c[3];
    if (h & 1) softmax_two(lg, phi[h - 1], phi[h]);
  }
  TSIF(par == 0 && w == 1, 65);
  wg_sync(1 + par);
  TSIF(par == 0 && w == 1, 66);
  const bool nohist = (w == 0) && (b < 8);
  const uint4* hp = g_halo + ((b - 8) * 2 + par) * 224 + lane;
  uint32_t tg[7];
  if (w > 0) {
    const uint4 v0 = lds128(xa + (w - 1) * 2560), v1 = lds128(xa + (w - 1) * 2560 + 512), v2 = lds128(xa + (w - 1) * 2560 + 1024);
    const uint4 v3 = lds128(xa + (w - 1) * 2560 + 1536), v4 = lds128(xa + (w - 1) * 2560 + 2048);
    kpv[0] = v0.x; kpv[1] = v0.y; kpv[2] = v0.z; kpv[3] = v0.w; kpv[4] = v1.x; kpv[5] = v1.y; kpv[6] = v1.z; kpv[7] = v1.w;
    kpv[8] = v2.x; kpv[9] = v2.y; vpv[0] = v2.z; vpv[1] = v2.w; vpv[2] = v3.x; vpv[3] = v3.y; vpv[4] = v3.z; vpv[5] = v3.w;
    vpv[6] = v4.x; vpv[7] = v4.y; vpv[8] = v4.z; vpv[9] = v4.w;
  } else if (nohist) {
#pragma unroll
    for (int j = 0; j < 10; j++) kpv[j] = vpv[j] = 0u;
  } else {
    TSIF(par == 0, 77);
    halo_read(kpv, vpv, tg, hp);
  }
  if (w == 0 && !nohist) {
    int spins = 0;
    while (true) {
      bool ok = true;
#pragma unroll
      for (int j = 0; j < 7; j++) ok = ok && tg[j] == tag;
      if (__all_sync(0xffffffffu, ok) || ++spins > SPIN_LIMIT) break;
      halo_read(kpv, vpv, tg, hp);
    }
    TSIF(par == 0, 79);
  }
#pragma unroll
  for (int h = 0; h < 4; h++) {
    const int f = h == 0 ? 0 : h == 1 ? 3 : h == 2 ? 5 : 8, hf = h < 2 ? 2 : 7;
    float a[4] = {0.f, 0.f, 0.f, 0.f};
    mma16816(a, qlo[f], qhi[f], qlo[f + 1], qhi[f + 1], kpv[f], kpv[f + 1]);
    mma1688(a, qml[h], qmh[h], kpv[hf]);
    const float ninf = __int_as_float(0xff800000);
    lg[h & 1][0] = far0 ? (nohist ? ninf : a[0]) : slo[h][0];
    lg[h & 1][1] = far1 ? (nohist ? ninf : a[1]) : slo[h][1];
    if (h & 1) softmax_two(lg, plo[h - 1], plo[h]);
  }
  TSIF(par == 0 && w <= 1, 67 + w);
  uint32_t ov[20];
#pragma unroll
  for (int hp = 0; hp < 2; hp++) {
    const int hf = hp ? 7 : 2;
    float sh[4] = {0.f, 0.f, 0.f, 0.f}, i0 = 0.f, i1 = 0.f;
#pragma unroll
    for (int e = 0; e < 2; e++) {
      const int h = 2 * hp + e, f = h == 0 ? 0 : h == 1 ? 3 : h == 2 ? 5 : 8;
      const uint32_t a0 = plo[h] & mfar, a2 = plo[h] & ~mfar, a3 = phi[h] & mfar, c1 = phi[h] & ~mfar;
      float sum[4] = {0.f, 0.f, 0.f, 0.f};
      mma1688(sum, plo[h], phi[h], 0x3F803F80u);
      const float r0 = rcp(sum[0]), r1 = rcp(sum[2]);
#pragma unroll
      for (int j = f; j < f + 2; j++) {
        float o[4] = {0.f, 0.f, 0.f, 0.f};
        mma16816(o, a0, 0u, a2, a3, vpv[j], vlo[j]);
        mma1688(o, 0u, c1, vhi[j]);
        ov[2 * j] = pack2(o[0] * r0, o[1] * r0);
        ov[2 * j + 1] = pack2(o[2] * r1, o[3] * r1);
      }
      const bool mine = e ? g >= 4 : g < 4;
      mma16816(sh, a0, 0u, a2, a3, mine ? vpv[hf] : 0u, mine ? vlo[hf] : 0u);
      mma1688(sh, 0u, c1, mine ? vhi[hf] : 0u);
      if (e == 0 || t >= 2) {
        i0 = r0;
        i1 = r1;
      }
    }
    ov[2 * hf] = pack2(sh[0] * i0, sh[1] * i0);
    ov[2 * hf + 1] = pack2(sh[2] * i1, sh[3] * i1);
  }
  TS(32 + 4 * par + w);
  mbar_wait(sb + OFF_BAR + 8 * B_P1, 0);
  const uint32_t oa = sb + OFF_OA + (lane >> 4) * 2048 + (32 * w + 2 * (lane & 15) + par) * 16;
#pragma unroll
  for (int j = 0; j < 5; j++) stsm4(oa + 4096 * j, ov + 4 * j);
  TSIF(par == 0 && w == 0, 120);
  fence_async_smem();
  TSIF(par == 0 && w == 0, 121);
  __syncwarp();
  if (lane == 0) mbar_arrive(sb + OFF_BAR + 8 * B_ATTN);
  TSM(w == 0 || w == 2, 122 + par + (w == 2 ? 3 : 0));
}

struct Maps {
  CUtensorMap x, wm, wt, k, v, y, wo, qm, qt, om, ot, yl, ol, wh;
};

__device__ __forceinline__ void load_stage(uint32_t sb, int kb, int b, const Maps& m) {
  const uint32_t st = sb + (kb & 3) * STAGE_BYTES, bar = sb + OFF_BAR + 8 * (B_FULL1 + (kb & 3));
  const int r = b >> 3, hg = b & 7, slab = kb - KV_KB;
  const bool kv = slab >= 0 && slab < 5;
  const uint32_t kbar = sb + OFF_BAR + 8 * (B_KV + slab), dst = sb + OFF_KVS + slab * KVS_BYTES;
  mbar_expect_tx(bar, STAGE_BYTES);
  if (kv) mbar_expect_tx(kbar, KVS_BYTES);
  tma_3d(st, &m.x, 64 * kb, 64 * r, 0, bar);
  tma_3d(st + ST_W, &m.wm, 80 * hg + (tail_first(hg) ? 16 : 0), 64 * kb, 0, bar);
  tma_3d(st + ST_WT, &m.wt, 80 * hg + (tail_first(hg) ? 0 : 64), 64 * kb, 0, bar);
  if (kv) tma_3d(dst, &m.k, 0, 32 * (b >> 1) - 3, 2 * slab + (b & 1), kbar);
  if (kv) tma_3d(dst + KVS_V, &m.v, 0, 32 * (b >> 1), 2 * slab + (b & 1), kbar);
}

__global__ void __launch_bounds__(NTHR, 1) fused_kernel(const __grid_constant__ Maps m, const Params p) {
  extern __shared__ __align__(1024) uint8_t smem[];
  const uint32_t sb = (uint32_t)__cvta_generic_to_shared(smem);
  const uint32_t bars = sb + OFF_BAR;
  const int tid = threadIdx.x, lane = tid & 31;
  int b = blockIdx.x;
  b = (((b & 63) >> 3) * 2 + (b & 1)) * 8 + (((b < 64 ? 0x6521 : 0x7430) >> (4 * ((b >> 1) & 3))) & 7);
  const int r = b >> 3, hg = b & 7;

  if (tid == T_ISSUE) {
    TSM(true, 0);
#pragma unroll
    for (int i = 0; i < 4; i++) mbar_init(bars + 8 * (B_F0 + i), 1);
    fence_async_smem();
#pragma unroll
    for (int i = 0; i < 4; i++) {
      mbar_expect_tx(bars + 8 * (B_F0 + i), (i ? 0 : ST_W) + 6144);
      if (i == 0) tma_3d(sb, &m.x, 0, 64 * r, 0, bars + 8 * B_F0);
      tma_3d(sb + ST_W + 6144 * i, &m.wh, 80 * hg + (tail_first(hg) ? 16 : 0), 16 * i, 0, bars + 8 * (B_F0 + i));
    }
#pragma unroll
    for (int i = 0; i < 4; i++) mbar_init(bars + 8 * (B_FULL1 + i), 1);
    fence_async_smem();
    mbar_expect_tx(bars + 8 * B_FULL1, STAGE_BYTES - ST_WT);
    tma_3d(sb + ST_WT, &m.wt, 80 * hg + (tail_first(hg) ? 0 : 64), 0, 0, bars + 8 * B_FULL1);
    load_stage(sb, 1, b, m);
  } else if (tid == T_INIT) {
#pragma unroll
    for (int i = 0; i < B_F0; i++) mbar_init(bars + 8 * i, i < B_GATE ? 8 : i < B_CVD ? 4 : i == B_CVD ? 20 : 1);
    fence_async_smem();
  }
  const int warp = __shfl_sync(0xffffffffu, tid >> 5, 0), wg = warp >> 2, w = warp & 3;
  __syncthreads();

  if (wg == 3) {
    asm volatile("setmaxnreg.dec.sync.aligned.u32 56;");
    if (w == 0) {
      if (lane == 0) {
#pragma unroll 1
        for (int kb = 2; kb < 10; kb++) {
          if (kb >= 4) mbar_wait(bars + 8 * (kb == 7 ? B_E3 : B_EMPTY1 + (kb & 3)), (kb >> 3) & 1);
          TSIF(kb >= 4, 44 + kb);
          load_stage(sb, kb, b, m);
          TSIF(kb == 3, 60);
          if (kb == 9) mbar_arrive(bars + 8 * B_LAST);
        }
        mbar_wait(bars + 8 * B_WOP, 0);
        mbar_wait(bars + 8 * B_EPOCH, 0);
        flag_wait(g_cnt + C_W + 32 * hg, (lds32(sb + OFF_EPOCH) + 1) * 16);
        TS(30);
#pragma unroll 1
        for (int j = 0; j < 8; j++) {
          if (j >= 6) mbar_wait(bars + 8 * (B_EMPTY2 + j - 6), 0);
          if (j == 4) mbar_wait(bars + 8 * B_ORB, 0);
          TSIF(j >= 6, 100 + j);
          mbar_expect_tx(bars + 8 * (B_FULL2 + j), j == 0 ? WO_BYTES : j == 5 ? O_BYTES + WO_BYTES + 512 : O_BYTES + WO_BYTES);
          bulk_load(sb + off_w(j), g_WO + (hg * 8 + step_src(hg, j)) * 800, WO_BYTES, bars + 8 * (B_FULL2 + j));
        }
        mbar_wait(bars + 8 * (B_EMPTY2 + 3), 0);
        mbar_expect_tx(bars + 8 * B_QF, O_BYTES);
        tma_2d(sb + OFF_QS, &m.qm, 80 * hg, 128 * r, bars + 8 * B_QF);
        tma_2d(sb + OFF_QT, &m.qt, 80 * hg + 64, 128 * r, bars + 8 * B_QF);
      }
    } else if (w == 1) {
      unsigned epoch = 0;
      if (lane == 0) {
        epoch = atomicAdd(g_cnt + C_LAUNCH, 1u) / NCTA;
        asm volatile("st.shared.u32 [%0], %1;" ::"r"(sb + OFF_EPOCH), "r"(epoch) : "memory");
        mbar_arrive(bars + 8 * B_EPOCH);
        mbar_wait(bars + 8 * B_KVD, 0);
        mbar_expect_tx(bars + 8 * B_HB, 5 * 4096);
#pragma unroll 1
        for (int c = 0; c < 5; c++) {
          if (c == 3) mbar_wait(bars + 8 * B_S3, 0);
          bulk_load(sb + off_ch(c) + U_BYTES, p.ssm_k + (5 * b + c) * SEQ, 4096, bars + 8 * B_HB);
        }
#pragma unroll
        for (int c = 0; c < 4; c++) mbar_expect_tx(bars + 8 * (B_U + c), c < 3 ? U_BYTES : 2 * U_BYTES);
        const uint4* usrc = g_U + 5 * b * U_PITCH;
        mbar_wait(bars + 8 * B_USIG, 0);
        flag_wait(g_cnt + C_PREP + 32 * (b & 15), (epoch + 1) * NCTA);
        TS(23);
#pragma unroll
        for (int c = 0; c < 5; c++) {
          if (c == 3) mbar_wait(bars + 8 * (B_U + 2), 0);
          bulk_load(sb + off_ch(c), usrc + c * U_PITCH, U_BYTES, bars + 8 * (B_U + (c < 3 ? c : 3)));
          TSIF(c == 0 || c == 4, 116 + (c >> 2));
        }
      }
      epoch = __shfl_sync(0xffffffffu, epoch, 0);
      if (lane < 8) {
        const int src = (b & ~7) | step_src(hg, lane);
        mbar_wait(bars + 8 * B_ATTN, 0);
        TS(20);
        bool seen = false;
#pragma unroll 1
        for (int spins = 0; spins < SPIN_LIMIT; spins++) {
          const bool now = !seen && (int)(flag_read(g_cnt + C_O + 32 * src) - (epoch + 1)) >= 0;
          if (now && lane >= 1 && lane < 4) bulk_load(sb + off_o(lane), g_O + src * 1280, O_BYTES, bars + 8 * (B_FULL2 + lane));
          seen = seen || now;
          if (__all_sync(0xff, seen)) break;
        }
        TS(21);
        if (lane == 5) bulk_load(sb + OFF_GATE, g_gate + 128 * r, 512, bars + 8 * (B_FULL2 + 5));
#pragma unroll 1
        for (int j = 4; j < 8; j++) {
          if (lane == j) {
            mbar_wait(bars + 8 * (j < 6 ? B_C34 : B_EMPTY2 + j - 6), 0);
            bulk_load(sb + off_o(j), g_O + src * 1280, O_BYTES, bars + 8 * (B_FULL2 + j));
          }
          __syncwarp(0xff);
        }
        TS(22);
      }
    } else if (w == 2) {
      mbar_wait(bars + 8 * B_PREP, 0);
      flag_signal(g_cnt + C_PREP, 16, lane);
      TS(25);
      if (lane == 0) {
        mbar_arrive(bars + 8 * B_USIG);
        mbar_expect_tx(bars + 8 * B_ORB, O_BYTES / 4 + 64);
        mbar_wait(bars + 8 * B_GATE, 0);
        publish(g_gate + 16 * b, sb + OFF_GATE + 64 * hg, 64);
        bulk_load(sb + OFF_GATE + 64 * hg, g_gate + 16 * b, 64, bars + 8 * B_ORB);
        mbar_wait(bars + 8 * B_ATTN, 0);
        publish(g_O + b * 1280, sb + OFF_OA, O_BYTES);
        tma_2d(sb + OFF_KVX + 10240, &m.ol, 48, b * 160, bars + 8 * B_ORB);
        TS(74);
        mbar_wait(bars + 8 * B_ORB, 0);
        flag_bump(g_cnt + C_O + 32 * b);
        TS(26);
      }
    } else {
      if (lane == 0) {
        uint4* dst = g_WO + (hg * 8 + (r >> 1)) * 800 + (r & 1) * 80;
        mbar_wait(bars + 8 * B_S3, 0);
        asm volatile("cp.async.bulk.prefetch.L2.global [%0], 6400;" ::"l"(p.wo + b * 3200) : "memory");
        mbar_wait(bars + 8 * B_P1, 0);
        mbar_wait(bars + 8 * WB_TRIG, 0);
        mbar_expect_tx(bars + 8 * B_WST, WO_BYTES / 2);
        tma_3d(sb + OFF_WA, &m.wo, 0, 40 * r, 5 * hg, bars + 8 * B_WST);
        mbar_wait(bars + 8 * B_WST, 0);
#pragma unroll 1
        for (int n = 0; n < 5; n++) bulk_store(dst + 160 * n, sb + OFF_WA + 1280 * n, 1280);
        bulk_wait_read();
        mbar_expect_tx(bars + 8 * B_WST, WO_BYTES / 2);
#pragma unroll 1
        for (int n = 0; n < 5; n++) bulk_load(sb + OFF_WA + 1280 * n, dst + 160 * n, 1280, bars + 8 * B_WST);
        mbar_wait(bars + 8 * B_WST, 1);
        flag_bump(g_cnt + C_W + 32 * hg);
        mbar_arrive(bars + 8 * B_WOP);
        TS(71);
        mbar_expect_tx(bars + 8 * B_C34, 3 * (U_BYTES / 4));
        mbar_expect_tx(bars + 8 * B_YRB, 2 * (U_BYTES / 4));
#pragma unroll 1
        for (int c = 0; c < 5; c++) {
          mbar_wait(bars + 8 * (B_YST + c), 0);
          publish(g_U + (5 * b + c) * U_PITCH, sb + off_ch(c), U_BYTES);
          tma_2d(sb + off_ch(c), &m.yl, 48, (5 * b + c) * (U_PITCH / 8), bars + 8 * (c < 3 ? B_C34 : B_YRB));
        }
        TS(75);
        mbar_wait(bars + 8 * B_C34, 0);
        mbar_wait(bars + 8 * B_YRB, 0);
        flag_bump(g_cnt + C_Y + 32 * (b >> 4));
        TS(27);
        mbar_expect_tx(bars + 8 * B_YFULL, 20480);
        flag_wait(g_cnt + C_Y + 32 * hg, (lds32(sb + OFF_EPOCH) + 1) * 16);
        TS(24);
        tma_2d(sb + OFF_YT, &m.y, 128 * r, 80 * hg, bars + 8 * B_YFULL);
        tma_2d(sb + OFF_YT + 10240, &m.y, 128 * r + 64, 80 * hg, bars + 8 * B_YFULL);
      }
    }
  } else {
    asm volatile("setmaxnreg.inc.sync.aligned.u32 152;");
    if (wg < 2) {
      float acc[120];
#pragma unroll
      for (int i = 0; i < 120; i++) acc[i] = 0.f;
      const uint32_t da = desc_lo(sb + wg * 8192, 16), db = desc_lo(sb + ST_W, 8192), dc = desc_lo(sb + ST_WT, 2048);
#pragma unroll
      for (int k = 0; k < 4; k++) {
        mbar_wait(bars + 8 * (B_F0 + k), 0);
        TSIF(w == 0 && wg == 0 && k == 0, 1);
        wg_fence();
        WgSST<192>::mma<HI_SW128, HI_SW128>(acc, da + 2 * k, desc_lo(sb + ST_W, 2048) + 384 * k, 1);
        wg_commit();
      }
      mbar_wait(bars + 8 * B_FULL1, 0);
      wg_fence();
#pragma unroll
      for (int k = 0; k < 4; k++) WgSST<48>::mma<HI_SW128, HI_SW32>(acc + 96, da + 2 * k, dc + 32 * k, 1);
      wg_commit();
#pragma unroll 1
      for (int kb = 1; kb < 10; kb++) {
        mbar_wait(bars + 8 * (B_FULL1 + (kb & 3)), (kb >> 2) & 1);
        const uint32_t so = (kb & 3) * (STAGE_BYTES >> 4);
        wg_fence();
#pragma unroll
        for (int k = 0; k < 4; k++) {
          WgSST<192>::mma<HI_SW128, HI_SW128>(acc, da + so + 2 * k, db + so + 128 * k, 1);
          WgSST<48>::mma<HI_SW128, HI_SW32>(acc + 96, da + so + 2 * k, dc + so + 32 * k, 1);
        }
        wg_commit();
        wg_wait<1>();
        if (lane == 0) mbar_arrive(bars + 8 * (kb == 4 ? B_E3 : B_EMPTY1 + ((kb - 1) & 3)));
      }
      mbar_wait(bars + 8 * B_EPOCH, 0);
      const uint32_t tag = lds32(sb + OFF_EPOCH) + 1;
      mbar_wait(bars + 8 * B_S3, 0);
      wg_wait<0>();
      pin<120>(acc);
      if (lane == 0) mbar_arrive(bars + 8 * B_P1);
      TSM(w == 0, 3 + wg);
      attention(acc, sb, b, wg, w, lane, tag);
    } else {
      const int tw = tid & 127, chl = 64 * (b & 1) + 8 * w + (lane >> 2);
      uint4* up = g_U + chl * U_PITCH + ((4 * (b >> 1) + (lane & 3)) ^ ((b >> 2) & 1));
      uint2 sw[10];
      uint32_t dv = 0;
      if (lane < 5) dv = __ldg(reinterpret_cast<const unsigned short*>(p.ssm_D) + 5 * b + lane);
#pragma unroll
      for (int i = 0; i < 10; i++) sw[i] = ldg64(reinterpret_cast<const uint2*>(p.shift_k) + chl + 128 * (i >> 1) + 32 * (i & 1));
      uint32_t tab[12];
      uint32_t tt[2];
      fft_tables(tab, tw);
      fft_twiddles(tt, tw);
      uint4 res[10];
#pragma unroll
      for (int i = 0; i < 10; i++) res[i] = make_uint4(0, 0, 0, 0);
#pragma unroll 1
      for (int slab = 0; slab < 5; slab++) {
#pragma unroll
        for (int i = 0; i < 8; i++) res[i] = res[i + 2];
        prep_slab(res + 8, sw, sb, slab, w, lane);
        TSIF(w == 0, 99 + 4 * slab);
#pragma unroll
        for (int i = 0; i < 8; i++) sw[i] = sw[i + 2];
      }
      TSIF(w == 0, 28);
      __syncwarp();
      if (lane == 0) mbar_arrive(bars + 8 * B_KVD + ((res[8].x ^ res[9].x) & p.zero));
      mbar_wait(bars + 8 * B_KVD, 0);
      fft_tables_store(tab, sb, tw);
      mbar_wait(bars + 8 * B_LAST, 0);
#pragma unroll
      for (int i = 0; i < 10; i++) up[(128 * (i >> 1) + 32 * (i & 1)) * U_PITCH] = res[i];
      __syncwarp();
      if (lane == 0) mbar_arrive(bars + 8 * B_PREP);
      TSIF(w == 0, 5);
      mbar_wait(bars + 8 * B_LAST, 0);
      prep_gate(p, sb, b, w, lane);
      __syncwarp();
      if (lane == 0) mbar_arrive(bars + 8 * B_GATE);
      TSIF(w == 0, 72);
      mbar_wait(bars + 8 * B_HB, 0);
      TSIF(w == 0, 2);
      const uint32_t ha = sb + U_BYTES + ((tw >> 3) * 16 + 8 + (tw & 7)) * 16;
      uint4 hv[5];
#pragma unroll
      for (int c = 0; c < 5; c++) hv[c] = lds128(ha + off_ch(c));
      __syncwarp();
#pragma unroll
      for (int c = 0; c < 5; c++) sts128((ha ^ 16) + off_ch(c), hv[c].x, hv[c].y, hv[c].z, hv[c].w);
      asm volatile("st.shared.v2.u32 [%0], {%1, %2};" ::"r"(sb + OFF_TT + 8 * tw), "r"(tt[0]), "r"(tt[1]) : "memory");
      if (tw < 5) asm volatile("st.shared.f32 [%0], %1;" ::"r"(sb + OFF_D + 4 * tw), "f"(bf_lo(dv) * 0.125f) : "memory");
      fence_async_smem();
      __syncwarp();
      if (lane == 0) mbar_arrive(bars + 8 * B_HA);
      TSIF(w == 0, 6);
    }

    FftConst fc;
    TSM(w == 0 && wg == 0, 104);
    mbar_wait(bars + 8 * B_HA, 0);
    fft_matrices(fc, sb, w, lane);
    TSM(w == 0 && wg == 0, 105);
    TSM(w == 0 && wg == 2, 124);
#pragma unroll 1
    for (uint32_t tasks = wg == 0 ? TASK0 : wg == 1 ? TASK1 : TASK2; tasks; tasks >>= 4) {
      const int c = (tasks & 7) - 1;
      conv_channel(fc, sb, c, wg, w, lane);
      if (lane == 0) mbar_arrive(bars + 8 * (B_YST + c));
      TSM(w == 0, 10 + c);
    }

    if (wg != 1) {
      const int wg = warp >> 3;
      const int g = lane >> 2;
      float acc[40];
#pragma unroll
      for (int i = 0; i < 40; i++) acc[i] = 0.f;
      const uint32_t da = desc_lo(sb + wg * 1024, 2048), db = desc_lo(sb, 2560);
      mbar_wait(bars + 8 * B_ORB, 0);
      mbar_wait(bars + 8 * B_FULL2, 0);
      TSM(w == 0, 15 + wg);
#pragma unroll 1
      for (int j = 0; j < 8; j++) {
        if (j == 1 - wg) mbar_wait(bars + 8 * B_CVD, 0);
        mbar_wait(bars + 8 * (B_FULL2 + j), 0);
        TSM(w == 0 && wg == 0, 44 + (j < 4 ? j : j + 6));
        const uint32_t oa = da + (off_o(j) >> 4), ob = db + (off_w(j) >> 4);
        wg_fence();
#pragma unroll
        for (int k = 0; k < 5; k++) WgSST<80>::mma<HI_NONE, HI_SW32>(acc, oa + 256 * k, ob + 32 * k, 1);
        wg_commit();
        wg_wait<1>();
        if (j >= 1 && j <= 4 && lane == 0) mbar_arrive(bars + 8 * (B_EMPTY2 + j - 1));
      }
      TSIF(w == 0 && wg == 0, 113);
      const int tr = 64 * wg + 16 * w + (lane & 15);
      const uint32_t fm = sb + OFF_QS + tr * 128, fx = (lane >> 4) ^ (tr & 7);
      const uint32_t ft = sb + OFF_QT + tr * 32 + (((lane >> 4) ^ (tr >> 2)) & 1) * 16;
      const float g0 = __uint_as_float(lds32(sb + OFF_GATE + (64 * wg + 16 * w + g) * 4));
      const float g1 = __uint_as_float(lds32(sb + OFF_GATE + (64 * wg + 16 * w + 8 + g) * 4));
      const uint32_t ga = pack2(g0, g0), gb = pack2(g1, g1);
      const uint32_t na = pack2(1.f - g0, 1.f - g0), nb = pack2(1.f - g1, 1.f - g1);

      uint32_t qf[20];
      mbar_wait(bars + 8 * B_QF, 0);
      TSM(w == 0 && wg == 0, 99);
#pragma unroll
      for (int j = 0; j < 5; j++) ldsm4(qf + 4 * j, j < 4 ? fm + ((fx ^ (2 * j)) << 4) : ft);
#pragma unroll
      for (int i = 0; i < 20; i++) {
        qf[i] = bmul((i & 1) ? gb : ga, qf[i]);
        asm volatile("" : "+r"(qf[i]));
      }

      wg_wait<0>();
      pin<40>(acc);
      TSM(w == 0, 17 + wg);
      uint32_t pb[20];
#pragma unroll
      for (int j = 0; j < 10; j++) {
        pb[2 * j] = bmul(na, pack2(acc[4 * j], acc[4 * j + 1]));
        pb[2 * j + 1] = bmul(nb, pack2(acc[4 * j + 2], acc[4 * j + 3]));
        asm volatile("" : "+r"(pb[2 * j]), "+r"(pb[2 * j + 1]));
      }
      const uint32_t ya = sb + OFF_YT + wg * 10240 + ((lane >> 4) * 8 + (lane & 7)) * 128 +
                          (((2 * w + (((lane >> 3) & 1) ^ wg)) ^ (lane & 7)) << 4);
      mbar_wait(bars + 8 * B_YFULL, 0);
      TSM(w == 0 && wg == 0, 19);
#pragma unroll
      for (int j = 0; j < 5; j++) {
        uint32_t y[4];
        ldsm4t(y, ya + 2048 * j);
#pragma unroll
        for (int i = 0; i < 4; i++)
          qf[4 * j + i] = bfma(qf[4 * j + i], y[i], pb[4 * j + i]);
      }
#pragma unroll
      for (int j = 0; j < 5; j++) stsm4(j < 4 ? fm + ((fx ^ (2 * j)) << 4) : ft, qf + 4 * j);
      fence_async_smem();
      __syncwarp();
      if (lane == 0) {
        const int row = 64 * wg + 16 * w;
        asm volatile("cp.async.bulk.tensor.2d.global.shared::cta.bulk_group [%0, {%2, %3}], [%1];"
                     ::"l"(&m.om), "r"(sb + OFF_QS + row * 128), "r"(80 * hg), "r"(128 * r + row) : "memory");
        asm volatile("cp.async.bulk.tensor.2d.global.shared::cta.bulk_group [%0, {%2, %3}], [%1];"
                     ::"l"(&m.ot), "r"(sb + OFF_QT + row * 32), "r"(80 * hg + 64), "r"(128 * r + row) : "memory");
        asm volatile("cp.async.bulk.commit_group;\ncp.async.bulk.wait_group.read 0;" ::: "memory");
      }
      TSM(w == 0 || w == 3, 40 + 2 * wg + (w & 1));
    }
  }
}

typedef CUresult (*EncodeFn)(CUtensorMap*, CUtensorMapDataType, cuuint32_t, void*, const cuuint64_t*, const cuuint64_t*,
                             const cuuint32_t*, const cuuint32_t*, CUtensorMapInterleave, CUtensorMapSwizzle,
                             CUtensorMapL2promotion, CUtensorMapFloatOOBfill);

void encode(EncodeFn fn, CUtensorMap* tm, const void* base, int rank, const cuuint64_t* dims, const cuuint64_t* strides,
            const cuuint32_t* box, CUtensorMapSwizzle swz) {
  const cuuint32_t ones[3] = {1, 1, 1};
  fn(tm, CU_TENSOR_MAP_DATA_TYPE_BFLOAT16, rank, const_cast<void*>(base), dims, strides, box, ones,
     CU_TENSOR_MAP_INTERLEAVE_NONE, swz, CU_TENSOR_MAP_L2_PROMOTION_L2_128B, CU_TENSOR_MAP_FLOAT_OOB_FILL_NONE);
}

}

extern "C" void kernel_launch(void* const* d_in, const int* in_sizes, int n_in, void* d_out, int out_size) {
  (void)in_sizes; (void)n_in; (void)out_size;
  Params p;
  p.q = (const __nv_bfloat16*)d_in[0];
  p.k = (const __nv_bfloat16*)d_in[1];
  p.v = (const __nv_bfloat16*)d_in[2];
  p.shift_k = (const __nv_bfloat16*)d_in[3];
  p.ssm_k = (const __nv_bfloat16*)d_in[4];
  p.ssm_D = (const __nv_bfloat16*)d_in[5];
  p.wqkv = (const __nv_bfloat16*)d_in[7];
  p.wo = (const __nv_bfloat16*)d_in[8];
  p.gate_w = (const __nv_bfloat16*)d_in[9];
  p.out = (__nv_bfloat16*)d_out;
  p.zero = 0;

  static EncodeFn fn = nullptr;
  static void *yaddr = nullptr, *oaddr = nullptr;
  if (!fn) {
    cudaDriverEntryPointQueryResult qr;
    void* f = nullptr;
    cudaGetDriverEntryPoint("cuTensorMapEncodeTiled", &f, cudaEnableDefault, &qr);
    fn = (EncodeFn)f;
    cudaGetSymbolAddress(&yaddr, g_U);
    cudaGetSymbolAddress(&oaddr, g_O);
    cudaFuncSetAttribute(fused_kernel, cudaFuncAttributeMaxDynamicSharedMemorySize, SMEM_BYTES);
  }
  Maps m;
  {
    const cuuint64_t dims[3] = {640, 1024, 2}, st[2] = {2560, 1280};
    const cuuint32_t box[3] = {64, 64, 2};
    encode(fn, &m.x, p.q, 3, dims, st, box, CU_TENSOR_MAP_SWIZZLE_128B);
  }
  {
    const cuuint64_t dims[3] = {640, 640, 3}, st[2] = {3840, 1280};
    const cuuint32_t box[3] = {64, 64, 3}, boxt[3] = {16, 64, 3};
    encode(fn, &m.wm, p.wqkv, 3, dims, st, box, CU_TENSOR_MAP_SWIZZLE_128B);
    encode(fn, &m.wt, p.wqkv, 3, dims, st, boxt, CU_TENSOR_MAP_SWIZZLE_32B);
    const cuuint32_t boxh[3] = {64, 16, 3};
    encode(fn, &m.wh, p.wqkv, 3, dims, st, boxh, CU_TENSOR_MAP_SWIZZLE_128B);
  }
  {
    const cuuint64_t dims[3] = {64, 2048, 10}, st[2] = {1280, 128};
    const cuuint32_t boxk[3] = {64, 35, 1}, boxv[3] = {64, 32, 1};
    encode(fn, &m.k, p.k, 3, dims, st, boxk, CU_TENSOR_MAP_SWIZZLE_128B);
    encode(fn, &m.v, p.v, 3, dims, st, boxv, CU_TENSOR_MAP_SWIZZLE_128B);
  }
  {
    const cuuint64_t dims[3] = {16, 640, 40}, st[2] = {1280, 32};
    const cuuint32_t box[3] = {16, 40, 5};
    encode(fn, &m.wo, p.wo, 3, dims, st, box, CU_TENSOR_MAP_SWIZZLE_32B);
  }
  {
    const cuuint64_t dims[2] = {2048, 640}, st[1] = {U_PITCH * 16};
    const cuuint32_t box[2] = {64, 80};
    encode(fn, &m.y, yaddr, 2, dims, st, box, CU_TENSOR_MAP_SWIZZLE_128B);
    const cuuint64_t dl[2] = {64, DIM * U_PITCH / 8}, dol[2] = {64, NCTA * 160}, sl[1] = {128};
    const cuuint32_t bl[2] = {16, 32}, bol[2] = {16, 160};
    encode(fn, &m.yl, yaddr, 2, dl, sl, bl, CU_TENSOR_MAP_SWIZZLE_NONE);
    encode(fn, &m.ol, oaddr, 2, dol, sl, bol, CU_TENSOR_MAP_SWIZZLE_NONE);
  }
  {
    const cuuint64_t dims[2] = {640, 2048}, st[1] = {1280};
    const cuuint32_t bqm[2] = {64, 128}, bqt[2] = {16, 128}, bom[2] = {64, 16}, bot[2] = {16, 16};
    encode(fn, &m.qm, p.q, 2, dims, st, bqm, CU_TENSOR_MAP_SWIZZLE_128B);
    encode(fn, &m.qt, p.q, 2, dims, st, bqt, CU_TENSOR_MAP_SWIZZLE_32B);
    encode(fn, &m.om, p.out, 2, dims, st, bom, CU_TENSOR_MAP_SWIZZLE_128B);
    encode(fn, &m.ot, p.out, 2, dims, st, bot, CU_TENSOR_MAP_SWIZZLE_32B);
  }
  fused_kernel<<<NCTA, NTHR, SMEM_BYTES>>>(m, p);
}
```

```cpp
#include <cuda.h>
#include <cuda_bf16.h>
#include <cuda_runtime.h>
#include <stdint.h>

namespace {

constexpr int SEQ = 2048, DIM = 640, NCTA = 128, NTHR = 512;

#define KV_KB 2
#define DEV_EXIT 0
#define FENCE_LO 0
#define FENCE_HI 0
#define WB_TRIG B_USIG
#define T_ISSUE 288
#define U_FROM 0
#define U_TO 4
#define T_INIT 448
#define TASK0 0x3
#define TASK1 0x52
#define TASK2 0x41

constexpr uint32_t STAGE_BYTES = 47104, ST_W = 16384, ST_WT = 40960;
constexpr uint32_t O_BYTES = 20480, WO_BYTES = 12800;
constexpr uint32_t OFF_OA = 0;
constexpr uint32_t OFF_QS = 3 * O_BYTES, OFF_QT = OFF_QS + 16384;
constexpr uint32_t OFF_WC = 81920;
constexpr uint32_t OFF_WA = 94720;
constexpr uint32_t OFF_GATE = 145920;
constexpr uint32_t OFF_TT = 146432;
constexpr uint32_t OFF_KVX = 148480;
constexpr uint32_t OFF_CH3 = 163840;
constexpr uint32_t CH_BYTES = 12288, U_BYTES = 4096;
constexpr uint32_t OFF_FT = 225280, OFF_GT = 229376;
constexpr uint32_t OFF_CH0 = 188416;
constexpr uint32_t OFF_KVS = OFF_CH0, KVS_V = 4480, KVS_BYTES = 8576;
constexpr uint32_t OFF_YT = 163840;
constexpr uint32_t OFF_BAR = 231936;
constexpr uint32_t SMEM_BYTES = OFF_BAR + 512;

enum : uint32_t {
  B_EMPTY1 = 0, B_S3 = 3, B_E3 = 4, B_EMPTY2 = 5, B_ATTN = 9, B_P1 = 10,
  B_GATE = 11, B_HA = 12, B_KVD = 13, B_PREP = 14, B_YST = 15,
  B_CVD = 20,
  B_FULL2 = 21, B_U = 29, B_KV = 33, B_HB = 38, B_C34 = 39, B_YRB = 40, B_YFULL = 41, B_EPOCH = 42, B_LAST = 43,
  B_WOP = 44, B_USIG = 45, B_WST = 46, B_QF = 47, B_ORB = 48,
  B_F0 = 49, B_FULL1 = 53
};
constexpr uint32_t OFF_EPOCH = OFF_BAR + 8 * 58, OFF_D = OFF_BAR + 8 * 60;
__device__ __forceinline__ uint32_t off_o(int j) { return j < 4 ? OFF_OA + j * O_BYTES : j < 6 ? OFF_CH0 + (j - 4) * O_BYTES : OFF_OA + (j - 6) * O_BYTES; }
__device__ __forceinline__ uint32_t off_w(int j) { return j < 4 ? OFF_WA + j * WO_BYTES : j == 4 ? OFF_KVX : j == 5 ? OFF_WC : OFF_WA + (j - 6) * WO_BYTES; }
__device__ __forceinline__ int step_src(int hg, int j) { return j == 0 ? hg : j <= hg ? j - 1 : j; }
__device__ __forceinline__ bool tail_first(int hg) { return (hg & 3) == 3; }
__device__ __forceinline__ uint32_t off_ch(int c) { return (c < 3 ? OFF_CH0 : OFF_CH3 - 3 * CH_BYTES) + c * CH_BYTES; }

#define U_PITCH 264
__device__ __align__(1024) uint4 g_U[DIM * U_PITCH];
__device__ __align__(128) uint4 g_O[NCTA * 1280];
__device__ uint4 g_WO[64 * 800];
__device__ uint4 g_halo[NCTA * 2 * 7 * 32];
__device__ __align__(128) float g_gate[SEQ];
__device__ unsigned g_cnt[32 * (1 + 2 * 16 + 8 + NCTA)];
constexpr int C_LAUNCH = 0, C_PREP = 32, C_Y = 32 * 17, C_W = 32 * 33, C_O = 32 * 41;

#define TSM(cond, slot) do { } while (0)
#define TSIF(cond, slot) do { if (__LINE__ >= FENCE_LO && __LINE__ < FENCE_HI) sched_fence(); } while (0)
__device__ __forceinline__ void sched_fence() {
  asm volatile("{\n.reg .pred p;\n.reg .u32 c;\nmov.u32 c, %%clock;\nsetp.eq.u32 p, c, 0;\n@p st.shared.u32 [%0], c;\n}"
               ::"r"(1024 + OFF_EPOCH + 4) : "memory");
}
#define TS(slot) TSIF(true, slot)

struct Params {
  const __nv_bfloat16 *q, *k, *v, *shift_k, *ssm_k, *ssm_D, *wqkv, *wo, *gate_w;
  __nv_bfloat16* out;
  uint32_t zero;
};

constexpr int SPIN_LIMIT = 1 << 17;

__device__ __forceinline__ void mbar_init(uint32_t bar, uint32_t count) {
  asm volatile("mbarrier.init.shared::cta.b64 [%0], %1;" ::"r"(bar), "r"(count) : "memory");
}
__device__ __forceinline__ void mbar_expect_tx(uint32_t bar, uint32_t bytes) {
  asm volatile("mbarrier.arrive.expect_tx.shared::cta.b64 _, [%0], %1;" ::"r"(bar), "r"(bytes) : "memory");
}
__device__ __forceinline__ void mbar_arrive(uint32_t bar) {
  asm volatile("mbarrier.arrive.shared::cta.b64 _, [%0];" ::"r"(bar) : "memory");
}
__device__ __forceinline__ void mbar_wait(uint32_t bar, uint32_t parity) {
  uint32_t ok;
  int spins = 0;
  do {
      asm volatile("{\n.reg .pred p;\nmbarrier.try_wait.parity.shared::cta.b64 p, [%1], %2;\nselp.b32 %0, 1, 0, p;\n}"
                   : "=r"(ok) : "r"(bar), "r"(parity) : "memory");
    if (++spins > SPIN_LIMIT) break;
  } while (!ok);
}
__device__ __forceinline__ unsigned flag_read(const unsigned* p) {
  unsigned v;
  asm volatile("ld.relaxed.gpu.global.u32 %0, [%1];" : "=r"(v) : "l"(p) : "memory");
  return v;
}
__device__ __forceinline__ void flag_poll(const unsigned* p, unsigned target) {
  unsigned v;
  int spins = 0;
  do {
    asm volatile("ld.relaxed.gpu.global.u32 %0, [%1];" : "=r"(v) : "l"(p) : "memory");
    if (++spins > SPIN_LIMIT) break;
  } while ((int)(v - target) < 0);
}
__device__ __forceinline__ void flag_wait(const unsigned* p, unsigned target) {
  flag_poll(p, target);
}
__device__ __forceinline__ void flag_signal(unsigned* p, int n, int lane) {
  if (lane == 0) asm volatile("fence.release.gpu;" ::: "memory");
  __syncwarp();
  if (lane < n) asm volatile("red.relaxed.gpu.global.add.u32 [%0], 1;" ::"l"(p + 32 * lane) : "memory");
}
__device__ __forceinline__ void flag_bump(unsigned* p) {
  asm volatile("red.relaxed.gpu.global.add.u32 [%0], 1;" ::"l"(p) : "memory");
}
__device__ __forceinline__ void fence_async_smem() { asm volatile("fence.proxy.async.shared::cta;" ::: "memory"); }
__device__ __forceinline__ void wg_sync(int id) { asm volatile("bar.sync %0, 128;" ::"r"(id) : "memory"); }

__device__ __forceinline__ void tma_2d(uint32_t dst, const CUtensorMap* tm, int c0, int c1, uint32_t bar) {
  asm volatile("cp.async.bulk.tensor.2d.shared::cluster.global.mbarrier::complete_tx::bytes [%0], [%1, {%3, %4}], [%2];"
               ::"r"(dst), "l"(tm), "r"(bar), "r"(c0), "r"(c1) : "memory");
}
__device__ __forceinline__ void tma_3d(uint32_t dst, const CUtensorMap* tm, int c0, int c1, int c2, uint32_t bar) {
  asm volatile("cp.async.bulk.tensor.3d.shared::cluster.global.mbarrier::complete_tx::bytes [%0], [%1, {%3, %4, %5}], [%2];"
               ::"r"(dst), "l"(tm), "r"(bar), "r"(c0), "r"(c1), "r"(c2) : "memory");
}
__device__ __forceinline__ void bulk_load(uint32_t dst, const void* src, uint32_t bytes, uint32_t bar) {
  asm volatile("cp.async.bulk.shared::cluster.global.mbarrier::complete_tx::bytes [%0], [%1], %2, [%3];"
               ::"r"(dst), "l"(src), "r"(bytes), "r"(bar) : "memory");
}
__device__ __forceinline__ void bulk_store(void* dst, uint32_t src, uint32_t bytes) {
  asm volatile("cp.async.bulk.global.shared::cta.bulk_group [%0], [%1], %2;" ::"l"(dst), "r"(src), "r"(bytes) : "memory");
}
__device__ __forceinline__ void bulk_wait_read() {
  asm volatile("cp.async.bulk.commit_group;\ncp.async.bulk.wait_group.read 0;" ::: "memory");
}

__device__ __forceinline__ void publish(void* dst, uint32_t src, uint32_t bytes) {
  bulk_store(dst, src, bytes);
  bulk_wait_read();
}

__device__ __forceinline__ void wg_fence() { asm volatile("wgmma.fence.sync.aligned;" ::: "memory"); }
__device__ __forceinline__ void wg_commit() { asm volatile("wgmma.commit_group.sync.aligned;" ::: "memory"); }
template <int N> __device__ __forceinline__ void wg_wait() { asm volatile("wgmma.wait_group.sync.aligned %0;" ::"n"(N) : "memory"); }
__device__ __forceinline__ uint32_t desc_lo(uint32_t addr, uint32_t lbo) { return ((addr & 0x3FFFF) >> 4) | ((lbo >> 4) << 16); }
constexpr uint32_t desc_hi(uint32_t sbo, uint32_t swz) { return (sbo >> 4) | (swz << 30); }
constexpr uint32_t HI_SW128 = desc_hi(1024, 1), HI_SW64 = desc_hi(512, 2), HI_SW32 = desc_hi(256, 3), HI_NONE = desc_hi(128, 0);
template <int N> __device__ __forceinline__ void pin(float* d) {
#pragma unroll
  for (int i = 0; i < N; i++) asm volatile("" : "+f"(d[i])::"memory");
}

__device__ __forceinline__ uint32_t lds32(uint32_t a) {
  uint32_t v;
  asm volatile("ld.volatile.shared.u32 %0, [%1];" : "=r"(v) : "r"(a) : "memory");
  return v;
}
__device__ __forceinline__ uint2 ldg64(const void* a) {
  uint2 v;
  asm volatile("ld.global.nc.v2.u32 {%0, %1}, [%2];" : "=r"(v.x), "=r"(v.y) : "l"(a) : "memory");
  return v;
}
__device__ __forceinline__ void ldsm4(uint32_t* r, uint32_t a) {
  asm volatile("ldmatrix.sync.aligned.m8n8.x4.shared.b16 {%0, %1, %2, %3}, [%4];"
               : "=r"(r[0]), "=r"(r[1]), "=r"(r[2]), "=r"(r[3]) : "r"(a) : "memory");
}
__device__ __forceinline__ void ldsm4t(uint32_t* r, uint32_t a) {
  asm volatile("ldmatrix.sync.aligned.m8n8.x4.trans.shared.b16 {%0, %1, %2, %3}, [%4];"
               : "=r"(r[0]), "=r"(r[1]), "=r"(r[2]), "=r"(r[3]) : "r"(a) : "memory");
}
__device__ __forceinline__ uint2 lds64(uint32_t a) {
  uint2 v;
  asm volatile("ld.shared.v2.u32 {%0, %1}, [%2];" : "=r"(v.x), "=r"(v.y) : "r"(a) : "memory");
  return v;
}
__device__ __forceinline__ uint4 lds128(uint32_t a) {
  uint4 v;
  asm volatile("ld.shared.v4.u32 {%0, %1, %2, %3}, [%4];" : "=r"(v.x), "=r"(v.y), "=r"(v.z), "=r"(v.w) : "r"(a) : "memory");
  return v;
}
__device__ __forceinline__ void sts128(uint32_t a, uint32_t x, uint32_t y, uint32_t z, uint32_t w) {
  asm volatile("st.shared.v4.u32 [%0], {%1, %2, %3, %4};" ::"r"(a), "r"(x), "r"(y), "r"(z), "r"(w) : "memory");
}
__device__ __forceinline__ void stsm4(uint32_t a, const uint32_t* r) {
  asm volatile("stmatrix.sync.aligned.m8n8.x4.shared.b16 [%0], {%1, %2, %3, %4};" ::"r"(a), "r"(r[0]), "r"(r[1]), "r"(r[2]), "r"(r[3]) : "memory");
}
__device__ __forceinline__ uint32_t pack2(float lo, float hi) {
  uint32_t r;
  asm("cvt.rn.bf16x2.f32 %0, %1, %2;" : "=r"(r) : "f"(hi), "f"(lo));
  return r;
}
__device__ __forceinline__ uint32_t movm(uint32_t a) {
  uint32_t d;
  asm volatile("movmatrix.sync.aligned.m8n8.trans.b16 %0, %1;" : "=r"(d) : "r"(a));
  return d;
}
__device__ __forceinline__ uint32_t bmul(uint32_t a, uint32_t b) {
  uint32_t d;
  asm("mul.rn.bf16x2 %0, %1, %2;" : "=r"(d) : "r"(a), "r"(b));
  return d;
}
__device__ __forceinline__ uint32_t badd(uint32_t a, uint32_t b) {
  uint32_t d;
  asm("add.rn.bf16x2 %0, %1, %2;" : "=r"(d) : "r"(a), "r"(b));
  return d;
}
__device__ __forceinline__ uint32_t bfma(uint32_t a, uint32_t b, uint32_t c) {
  uint32_t d;
  asm("fma.rn.bf16x2 %0, %1, %2, %3;" : "=r"(d) : "r"(a), "r"(b), "r"(c));
  return d;
}
__device__ __forceinline__ float bf_lo(uint32_t x) { return __uint_as_float(x << 16); }
__device__ __forceinline__ float bf_hi(uint32_t x) { return __uint_as_float(x & 0xFFFF0000u); }
__device__ __forceinline__ float ex2(float x) {
  float y;
  asm("ex2.approx.ftz.f32 %0, %1;" : "=f"(y) : "f"(x));
  return y;
}
__device__ __forceinline__ float rcp(float x) {
  float y;
  asm("rcp.approx.ftz.f32 %0, %1;" : "=f"(y) : "f"(x));
  return y;
}
__device__ __forceinline__ void mma16816(float* d, uint32_t a0, uint32_t a1, uint32_t a2, uint32_t a3, uint32_t b0, uint32_t b1) {
  asm volatile("mma.sync.aligned.m16n8k16.row.col.f32.bf16.bf16.f32 {%0, %1, %2, %3}, {%4, %5, %6, %7}, {%8, %9}, {%0, %1, %2, %3};"
               : "+f"(d[0]), "+f"(d[1]), "+f"(d[2]), "+f"(d[3])
               : "r"(a0), "r"(a1), "r"(a2), "r"(a3), "r"(b0), "r"(b1));
}
__device__ __forceinline__ void mma1688(float* d, uint32_t a0, uint32_t a1, uint32_t b0) {
  asm volatile("mma.sync.aligned.m16n8k8.row.col.f32.bf16.bf16.f32 {%0, %1, %2, %3}, {%4, %5}, {%6}, {%0, %1, %2, %3};"
               : "+f"(d[0]), "+f"(d[1]), "+f"(d[2]), "+f"(d[3])
               : "r"(a0), "r"(a1), "r"(b0));
}

template <int N> struct WgRS;
template <int N> struct WgSST;
template <> struct WgRS<32> {
  template <uint32_t HB>
  static __device__ __forceinline__ void mma(float* d, const uint32_t* a, uint32_t db) {
    asm volatile("{\n.reg .pred p;\n.reg .b64 db;\nsetp.ne.b32 p, %22, 0;\n"
      "mov.b64 db, {%20, %21};\n"
      "wgmma.mma_async.sync.aligned.m64n32k16.f32.bf16.bf16 {"
      "%0, %1, %2, %3, %4, %5, %6, %7, %8, %9, %10, %11, %12, %13, %14, %15"
      "}, {%16, %17, %18, %19}, db, p, 1, 1, 1;\n}\n"
      : "+f"(d[0]), "+f"(d[1]), "+f"(d[2]), "+f"(d[3]), "+f"(d[4]), "+f"(d[5]), "+f"(d[6]), "+f"(d[7]),
        "+f"(d[8]), "+f"(d[9]), "+f"(d[10]), "+f"(d[11]), "+f"(d[12]), "+f"(d[13]), "+f"(d[14]), "+f"(d[15])
      : "r"(a[0]), "r"(a[1]), "r"(a[2]), "r"(a[3]), "r"(db), "n"(HB), "n"(1));
  }
  template <uint32_t HB>
  static __device__ __forceinline__ void set(float* d, const uint32_t* a, uint32_t db) {
    asm volatile("{\n.reg .pred p;\n.reg .b64 db;\nsetp.ne.b32 p, %22, 0;\n"
      "mov.b64 db, {%20, %21};\n"
      "wgmma.mma_async.sync.aligned.m64n32k16.f32.bf16.bf16 {"
      "%0, %1, %2, %3, %4, %5, %6, %7, %8, %9, %10, %11, %12, %13, %14, %15"
      "}, {%16, %17, %18, %19}, db, p, 1, 1, 1;\n}\n"
      : "=f"(d[0]), "=f"(d[1]), "=f"(d[2]), "=f"(d[3]), "=f"(d[4]), "=f"(d[5]), "=f"(d[6]), "=f"(d[7]),
        "=f"(d[8]), "=f"(d[9]), "=f"(d[10]), "=f"(d[11]), "=f"(d[12]), "=f"(d[13]), "=f"(d[14]), "=f"(d[15])
      : "r"(a[0]), "r"(a[1]), "r"(a[2]), "r"(a[3]), "r"(db), "n"(HB), "n"(0));
  }
};
template <> struct WgRS<64> {
  template <uint32_t HB>
  static __device__ __forceinline__ void mma(float* d, const uint32_t* a, uint32_t db) {
    asm volatile("{\n.reg .pred p;\n.reg .b64 db;\nsetp.ne.b32 p, %38, 0;\n"
      "mov.b64 db, {%36, %37};\n"
      "wgmma.mma_async.sync.aligned.m64n64k16.f32.bf16.bf16 {"
      "%0, %1, %2, %3, %4, %5, %6, %7, %8, %9, %10, %11, %12, %13, %14, %15, "
      "%16, %17, %18, %19, %20, %21, %22, %23, %24, %25, %26, %27, %28, %29, %30, %31"
      "}, {%32, %33, %34, %35}, db, p, 1, 1, 1;\n}\n"
      : "+f"(d[0]), "+f"(d[1]), "+f"(d[2]), "+f"(d[3]), "+f"(d[4]), "+f"(d[5]), "+f"(d[6]), "+f"(d[7]),
        "+f"(d[8]), "+f"(d[9]), "+f"(d[10]), "+f"(d[11]), "+f"(d[12]), "+f"(d[13]), "+f"(d[14]), "+f"(d[15]),
        "+f"(d[16]), "+f"(d[17]), "+f"(d[18]), "+f"(d[19]), "+f"(d[20]), "+f"(d[21]), "+f"(d[22]), "+f"(d[23]),
        "+f"(d[24]), "+f"(d[25]), "+f"(d[26]), "+f"(d[27]), "+f"(d[28]), "+f"(d[29]), "+f"(d[30]), "+f"(d[31])
      : "r"(a[0]), "r"(a[1]), "r"(a[2]), "r"(a[3]), "r"(db), "n"(HB), "n"(1));
  }
  template <uint32_t HB>
  static __device__ __forceinline__ void set(float* d, const uint32_t* a, uint32_t db) {
    asm volatile("{\n.reg .pred p;\n.reg .b64 db;\nsetp.ne.b32 p, %38, 0;\n"
      "mov.b64 db, {%36, %37};\n"
      "wgmma.mma_async.sync.aligned.m64n64k16.f32.bf16.bf16 {"
      "%0, %1, %2, %3, %4, %5, %6, %7, %8, %9, %10, %11, %12, %13, %14, %15, "
      "%16, %17, %18, %19, %20, %21, %22, %23, %24, %25, %26, %27, %28, %29, %30, %31"
      "}, {%32, %33, %34, %35}, db, p, 1, 1, 1;\n}\n"
      : "=f"(d[0]), "=f"(d[1]), "=f"(d[2]), "=f"(d[3]), "=f"(d[4]), "=f"(d[5]), "=f"(d[6]), "=f"(d[7]),
        "=f"(d[8]), "=f"(d[9]), "=f"(d[10]), "=f"(d[11]), "=f"(d[12]), "=f"(d[13]), "=f"(d[14]), "=f"(d[15]),
        "=f"(d[16]), "=f"(d[17]), "=f"(d[18]), "=f"(d[19]), "=f"(d[20]), "=f"(d[21]), "=f"(d[22]), "=f"(d[23]),
        "=f"(d[24]), "=f"(d[25]), "=f"(d[26]), "=f"(d[27]), "=f"(d[28]), "=f"(d[29]), "=f"(d[30]), "=f"(d[31])
      : "r"(a[0]), "r"(a[1]), "r"(a[2]), "r"(a[3]), "r"(db), "n"(HB), "n"(0));
  }
};
template <> struct WgSST<48> {
  template <uint32_t HA, uint32_t HB>
  static __device__ __forceinline__ void mma(float* d, uint32_t da, uint32_t db, int sc) {
    asm volatile("{\n.reg .pred p;\n.reg .b64 da, db;\nsetp.ne.b32 p, %28, 0;\n"
      "mov.b64 da, {%24, %25};\nmov.b64 db, {%26, %27};\n"
      "wgmma.mma_async.sync.aligned.m64n48k16.f32.bf16.bf16 {"
      "%0, %1, %2, %3, %4, %5, %6, %7, %8, %9, %10, %11, %12, %13, %14, %15, "
      "%16, %17, %18, %19, %20, %21, %22, %23"
      "}, da, db, p, 1, 1, 0, 1;\n}\n"
      : "+f"(d[0]), "+f"(d[1]), "+f"(d[2]), "+f"(d[3]), "+f"(d[4]), "+f"(d[5]), "+f"(d[6]), "+f"(d[7]),
        "+f"(d[8]), "+f"(d[9]), "+f"(d[10]), "+f"(d[11]), "+f"(d[12]), "+f"(d[13]), "+f"(d[14]), "+f"(d[15]),
        "+f"(d[16]), "+f"(d[17]), "+f"(d[18]), "+f"(d[19]), "+f"(d[20]), "+f"(d[21]), "+f"(d[22]), "+f"(d[23])
      : "r"(da), "n"(HA), "r"(db), "n"(HB), "r"(sc));
  }
};
template <> struct WgSST<80> {
  template <uint32_t HA, uint32_t HB>
  static __device__ __forceinline__ void mma(float* d, uint32_t da, uint32_t db, int sc) {
    asm volatile("{\n.reg .pred p;\n.reg .b64 da, db;\nsetp.ne.b32 p, %44, 0;\n"
      "mov.b64 da, {%40, %41};\nmov.b64 db, {%42, %43};\n"
      "wgmma.mma_async.sync.aligned.m64n80k16.f32.bf16.bf16 {"
      "%0, %1, %2, %3, %4, %5, %6, %7, %8, %9, %10, %11, %12, %13, %14, %15, "
      "%16, %17, %18, %19, %20, %21, %22, %23, %24, %25, %26, %27, %28, %29, %30, %31, "
      "%32, %33, %34, %35, %36, %37, %38, %39"
      "}, da, db, p, 1, 1, 0, 1;\n}\n"
      : "+f"(d[0]), "+f"(d[1]), "+f"(d[2]), "+f"(d[3]), "+f"(d[4]), "+f"(d[5]), "+f"(d[6]), "+f"(d[7]),
        "+f"(d[8]), "+f"(d[9]), "+f"(d[10]), "+f"(d[11]), "+f"(d[12]), "+f"(d[13]), "+f"(d[14]), "+f"(d[15]),
        "+f"(d[16]), "+f"(d[17]), "+f"(d[18]), "+f"(d[19]), "+f"(d[20]), "+f"(d[21]), "+f"(d[22]), "+f"(d[23]),
        "+f"(d[24]), "+f"(d[25]), "+f"(d[26]), "+f"(d[27]), "+f"(d[28]), "+f"(d[29]), "+f"(d[30]), "+f"(d[31]),
        "+f"(d[32]), "+f"(d[33]), "+f"(d[34]), "+f"(d[35]), "+f"(d[36]), "+f"(d[37]), "+f"(d[38]), "+f"(d[39])
      : "r"(da), "n"(HA), "r"(db), "n"(HB), "r"(sc));
  }
};
template <> struct WgSST<192> {
  template <uint32_t HA, uint32_t HB>
  static __device__ __forceinline__ void mma(float* d, uint32_t da, uint32_t db, int sc) {
    asm volatile("{\n.reg .pred p;\n.reg .b64 da, db;\nsetp.ne.b32 p, %100, 0;\n"
      "mov.b64 da, {%96, %97};\nmov.b64 db, {%98, %99};\n"
      "wgmma.mma_async.sync.aligned.m64n192k16.f32.bf16.bf16 {"
      "%0, %1, %2, %3, %4, %5, %6, %7, %8, %9, %10, %11, %12, %13, %14, %15, "
      "%16, %17, %18, %19, %20, %21, %22, %23, %24, %25, %26, %27, %28, %29, %30, %31, "
      "%32, %33, %34, %35, %36, %37, %38, %39, %40, %41, %42, %43, %44, %45, %46, %47, "
      "%48, %49, %50, %51, %52, %53, %54, %55, %56, %57, %58, %59, %60, %61, %62, %63, "
      "%64, %65, %66, %67, %68, %69, %70, %71, %72, %73, %74, %75, %76, %77, %78, %79, "
      "%80, %81, %82, %83, %84, %85, %86, %87, %88, %89, %90, %91, %92, %93, %94, %95"
      "}, da, db, p, 1, 1, 0, 1;\n}\n"
      : "+f"(d[0]), "+f"(d[1]), "+f"(d[2]), "+f"(d[3]), "+f"(d[4]), "+f"(d[5]), "+f"(d[6]), "+f"(d[7]),
        "+f"(d[8]), "+f"(d[9]), "+f"(d[10]), "+f"(d[11]), "+f"(d[12]), "+f"(d[13]), "+f"(d[14]), "+f"(d[15]),
        "+f"(d[16]), "+f"(d[17]), "+f"(d[18]), "+f"(d[19]), "+f"(d[20]), "+f"(d[21]), "+f"(d[22]), "+f"(d[23]),
        "+f"(d[24]), "+f"(d[25]), "+f"(d[26]), "+f"(d[27]), "+f"(d[28]), "+f"(d[29]), "+f"(d[30]), "+f"(d[31]),
        "+f"(d[32]), "+f"(d[33]), "+f"(d[34]), "+f"(d[35]), "+f"(d[36]), "+f"(d[37]), "+f"(d[38]), "+f"(d[39]),
        "+f"(d[40]), "+f"(d[41]), "+f"(d[42]), "+f"(d[43]), "+f"(d[44]), "+f"(d[45]), "+f"(d[46]), "+f"(d[47]),
        "+f"(d[48]), "+f"(d[49]), "+f"(d[50]), "+f"(d[51]), "+f"(d[52]), "+f"(d[53]), "+f"(d[54]), "+f"(d[55]),
        "+f"(d[56]), "+f"(d[57]), "+f"(d[58]), "+f"(d[59]), "+f"(d[60]), "+f"(d[61]), "+f"(d[62]), "+f"(d[63]),
        "+f"(d[64]), "+f"(d[65]), "+f"(d[66]), "+f"(d[67]), "+f"(d[68]), "+f"(d[69]), "+f"(d[70]), "+f"(d[71]),
        "+f"(d[72]), "+f"(d[73]), "+f"(d[74]), "+f"(d[75]), "+f"(d[76]), "+f"(d[77]), "+f"(d[78]), "+f"(d[79]),
        "+f"(d[80]), "+f"(d[81]), "+f"(d[82]), "+f"(d[83]), "+f"(d[84]), "+f"(d[85]), "+f"(d[86]), "+f"(d[87]),
        "+f"(d[88]), "+f"(d[89]), "+f"(d[90]), "+f"(d[91]), "+f"(d[92]), "+f"(d[93]), "+f"(d[94]), "+f"(d[95])
      : "r"(da), "n"(HA), "r"(db), "n"(HB), "r"(sc));
  }
};

struct FftConst {
  uint32_t f[2][4], fi[4][4];
  uint32_t ta[2][2], tb[2][2];
};
__device__ __forceinline__ void cis(int m, float scale, float& c, float& s) {
  const float a = (float)m * (-6.283185307179586f * scale);
  c = __cosf(a);
  s = __sinf(a);
}
__device__ __forceinline__ void fft_tables(uint32_t (&v)[12], int tw) {
  const int row = tw >> 2, ch = tw & 3;
#pragma unroll
  for (int i = 0; i < 4; i++) {
    float c[2], s[2], x[2];
#pragma unroll
    for (int e = 0; e < 2; e++) {
      cis((((32 * (8 * ch + 2 * i + e) + 15) * (4 * row - 63) + 2048) & 4095) - 2048, 1.f / 4096, c[e], s[e]);
      float gc, gs;
      cis((((row & 15) * (8 * (ch & 1) + 2 * i + e) + 8) & 15) - 8, 1.f / 16, gc, gs);
      x[e] = (row >> 4) == (ch >> 1) ? gc : (ch >> 1) ? gs : -gs;
    }
    v[i] = pack2(c[0] * 0.125f, c[1] * 0.125f);
    v[4 + i] = pack2(s[0] * 0.125f, s[1] * 0.125f);
    v[8 + i] = pack2(x[0], x[1]);
  }
#pragma unroll
  for (int i = 0; i < 12; i++) asm volatile("" : "+r"(v[i]));
}
__device__ __forceinline__ void fft_tables_store(const uint32_t (&v)[12], uint32_t sb, int tw) {
  const int row = tw >> 2;
  const uint32_t x = ((tw ^ (row >> 1)) & 3) << 4, a = sb + OFF_FT + (16 * (row >> 3) + (row & 7)) * 64 + x;
  sts128(a, v[0], v[1], v[2], v[3]);
  sts128(a + 512, v[4], v[5], v[6], v[7]);
  sts128(sb + OFF_GT + row * 64 + x, v[8], v[9], v[10], v[11]);
}
__device__ __forceinline__ void fft_twiddles(uint32_t (&v)[2], int tw) {
  float a[2], s[2];
#pragma unroll
  for (int i = 0; i < 2; i++) {
    float c;
    cis((2 * (2 * (tw & 3) + i) - 15) * (4 * (tw >> 2) - 63), 1.f / 4096, c, s[i]);
    a[i] = __fdividef(-s[i], 1.f + c);
  }
  v[0] = pack2(a[0], a[1]);
  v[1] = pack2(s[0], s[1]);
  asm volatile("" : "+r"(v[0]), "+r"(v[1]));
}
__device__ __forceinline__ void fft_matrices(FftConst& k, uint32_t sb, int w, int lane) {
  const uint32_t x = (lane >> 1) & 3;
  const uint2 t0 = lds64(sb + OFF_TT + 256 * w + 8 * lane), t1 = lds64(sb + OFF_TT + 256 * w + 8 * (lane ^ 3));
  k.ta[0][0] = t0.x;
  k.tb[0][0] = t0.y;
  k.ta[1][1] = __byte_perm(t1.x, 0, 0x1032);
  k.tb[1][1] = __byte_perm(t1.y, 0, 0x1032);
#pragma unroll
  for (int j = 0; j < 2; j++) {
    k.ta[1 - j][j] = k.ta[j][j] ^ 0x80008000u;
    k.tb[1 - j][j] = k.tb[j][j] ^ 0x80008000u;
    asm volatile("" : "+r"(k.ta[0][j]), "+r"(k.tb[0][j]), "+r"(k.ta[1][j]), "+r"(k.tb[1][j]));
  }
#pragma unroll
  for (int i = 0; i < 2; i++) {
    ldsm4(k.f[i], sb + OFF_FT + (16 * w + (lane & 15)) * 64 + (((2 * i + (lane >> 4)) ^ x) << 4));
    ldsm4t(k.fi[i], sb + OFF_FT + (32 * i + lane) * 64 + ((w ^ x) << 4));
#pragma unroll
    for (int j = 0; j < 4; j++) {
      k.fi[2 + i][j] = (j & 1) ? k.fi[i][j - 1] ^ 0x80008000u : k.fi[i][j + 1];
      asm volatile("" : "+r"(k.fi[2 + i][j]));
    }
  }
}
__device__ __forceinline__ void rot(uint32_t& x, uint32_t& y, uint32_t a, uint32_t b) {
  x = bfma(a, y, x);
  y = bfma(b, x, y);
  x = bfma(a, y, x);
}
__device__ __forceinline__ void twiddle_fwd(uint32_t (&a)[4][4], float* d, const FftConst& k) {
#pragma unroll
  for (int q = 0; q < 4; q++)
#pragma unroll
    for (int j = 0; j < 2; j++) {
      const float* x = d + 8 * q + 4 * j;
      uint32_t re = pack2(x[0], x[1]), im = pack2(x[2], x[3]);
      rot(re, im, k.ta[0][j], k.tb[0][j]);
      a[q & 2][2 * j + (q & 1)] = re;
      a[(q & 2) + 1][2 * j + (q & 1)] = im;
    }
}
__device__ __forceinline__ void g_step(float* d, const uint32_t (&a)[4][4], uint32_t dre, uint32_t dim) {
  WgRS<32>::set<HI_SW64>(d, a[0], dre);
  WgRS<32>::set<HI_SW64>(d + 16, a[2], dre);
  WgRS<32>::mma<HI_SW64>(d, a[1], dim);
  WgRS<32>::mma<HI_SW64>(d + 16, a[3], dim);
  wg_commit();
}

__device__ __forceinline__ void products(uint32_t (&a)[4][4], const float* H, const float* U, int p) {
#pragma unroll
  for (int j = 0; j < 2; j++)
#pragma unroll
    for (int m = 2 * p; m < 2 * p + 2; m++) {
      float pr[2], pi[2];
#pragma unroll
      for (int x = 0; x < 2; x++)
#pragma unroll
        for (int q = 0; q <= m; q++) {
          const int ih = 16 * (q >> 1) + 2 * (q & 1) + 4 * j + x, iu = 16 * ((m - q) >> 1) + 2 * ((m - q) & 1) + 4 * j + x;
          pr[x] = q ? fmaf(H[ih], U[iu], pr[x]) : H[ih] * U[iu];
          pi[x] = q ? fmaf(H[ih], U[iu + 8], pi[x]) : H[ih] * U[iu + 8];
          pr[x] = fmaf(-H[ih + 8], U[iu + 8], pr[x]);
          pi[x] = fmaf(H[ih + 8], U[iu], pi[x]);
        }
      a[m & 2][2 * j + (m & 1)] = pack2(pr[0], pr[1]);
      a[(m & 2) + 1][2 * j + (m & 1)] = pack2(pi[0], pi[1]);
    }
}

__device__ __forceinline__ void conv_channel(const FftConst& k, uint32_t sb, int c, int wg, int w, int lane) {
  const uint32_t cb = sb + off_ch(c), bars = sb + OFF_BAR;
  const uint32_t du = desc_lo(cb, 1024), dg = desc_lo(sb + OFF_GT, 16), dz = desc_lo(cb + U_BYTES, 16);
  float U[32], H[32];
  uint32_t a[4][4], e[4][4];
  const float dv = __uint_as_float(lds32(sb + OFF_D + 4 * c));
  wg_fence();
  WgRS<64>::set<HI_SW32>(H, k.f[0], du + 256);
  WgRS<64>::mma<HI_SW32>(H, k.f[1], du + 256 + 32);
  wg_commit();
  wg_wait<0>();
  pin<32>(H);
  twiddle_fwd(a, H, k);
  mbar_wait(bars + 8 * (B_U + (c < 3 ? c : 3)), 0);
  TSM(w == 0 && c < 3, 7 + wg);
  wg_fence();
  WgRS<64>::set<HI_SW32>(U, k.f[0], du);
  WgRS<64>::mma<HI_SW32>(U, k.f[1], du + 32);
  wg_commit();
  g_step(H, a, dg, dg + 64);
  wg_wait<1>();
  pin<32>(U);
  twiddle_fwd(e, U, k);
  wg_fence();
  g_step(U, e, dg, dg + 64);
  wg_wait<0>();
  pin<32>(U);
  pin<32>(H);
#pragma unroll
  for (int j = 0; j < 4; j++) H[4 * (j >> 1) + (j & 1)] += dv;
  float V[32];
#pragma unroll
  for (int p = 0; p < 2; p++) {
    products(a, H, U, p);
    wg_fence();
    WgRS<32>::set<HI_SW64>(V + 16 * p, a[2 * p], dg + 64);
    WgRS<32>::mma<HI_SW64>(V + 16 * p, a[2 * p + 1], dg);
    wg_commit();
  }
  const uint32_t za = cb + U_BYTES + (8 * w + (lane & 7)) * 128 + (((lane >> 3) ^ (lane & 7)) << 4);
  const uint32_t ya = cb + (lane >> 4) * 1024 + (8 * w + (lane & 7)) * 32 + ((((lane >> 3) ^ (lane >> 2)) & 1) << 4);
  wg_sync(1 + wg);
#pragma unroll
  for (int p = 0; p < 2; p++) {
    if (p == 0) wg_wait<1>();
    else wg_wait<0>();
    pin<16>(V + 16 * p);
#pragma unroll
    for (int i = 0; i < 4; i++) {
      const int j = i & 1;
      const float* x = V + 16 * p + 4 * j + (i & 2);
      e[p][i] = pack2(x[8], x[9]);
      e[2 + p][i] = pack2(x[0], x[1]);
      rot(e[p][i], e[2 + p][i], k.ta[1][j], k.tb[1][j]);
    }
    stsm4(za ^ (64 * p), e[p]);
    stsm4((za ^ (64 * p)) + 4096, e[2 + p]);
  }
  fence_async_smem();
  wg_sync(1 + wg);
  wg_fence();
  WgRS<64>::set<HI_SW128>(H, k.fi[0], dz);
#pragma unroll
  for (int ks = 1; ks < 4; ks++) WgRS<64>::mma<HI_SW128>(H, k.fi[ks], dz + 128 * ks);
  wg_commit();
  wg_wait<0>();
  pin<32>(H);
  if (lane == 0) mbar_arrive(bars + 8 * B_CVD);
  TSIF(w == 0, 88 + c);
#pragma unroll
  for (int j = 0; j < 8; j++)
    a[j >> 2][j & 3] = j < 2 ? pack2(H[4 * j], H[4 * j + 1]) : pack2(H[4 * j] + H[4 * j - 6], H[4 * j + 1] + H[4 * j - 5]);
  stsm4(ya, a[0]);
  stsm4(ya + 2048, a[1]);
  fence_async_smem();
  __syncwarp();
}

__device__ __forceinline__ void prep_slab(uint4* res, const uint2* sw, uint32_t sb, int slab, int w, int lane) {
  const int t = lane & 3, tp = (lane & 7) >> 1, pos = 8 * tp + 2 * (((lane >> 3) + tp) & 3) + (lane & 1);
  const uint32_t base = sb + OFF_KVS + slab * KVS_BYTES + pos * 128;
  uint32_t kk[2][4][4], vv[2][4];
  mbar_wait(sb + OFF_BAR + 8 * (B_KV + slab), 0);
#pragma unroll
  for (int h = 0; h < 2; h++) {
#pragma unroll
    for (int j = 0; j < 4; j++) {
      const uint32_t a = base + 128 * j;
      ldsm4t(kk[h][j], a + (((w + 4 * h) ^ ((a >> 7) & 7)) << 4));
    }
    const uint32_t a = base + KVS_V;
    ldsm4t(vv[h], a + (((w + 4 * h) ^ ((a >> 7) & 7)) << 4));
  }
#pragma unroll
  for (int h = 0; h < 2; h++) {
    uint32_t (&k)[4][4] = kk[h];
    uint32_t (&v)[4] = vv[h];
    const uint32_t w0 = __byte_perm(sw[h].x, 0, 0x1010), w1 = __byte_perm(sw[h].x, 0, 0x3232);
    const uint32_t w2 = __byte_perm(sw[h].y, 0, 0x1010), w3 = __byte_perm(sw[h].y, 0, 0x3232);
#pragma unroll
    for (int m = 0; m < 4; m++)
      v[m] = bmul(badd(badd(badd(bmul(k[0][m], w3), bmul(k[1][m], w2)), bmul(k[2][m], w1)), bmul(k[3][m], w0)), v[m]);
    uint32_t a[4];
#pragma unroll
    for (int m = 0; m < 4; m++) a[m] = (t & 1) ? v[(m + 3) & 3] : v[m];
    res[h] = (t & 2) ? make_uint4(a[2], a[3], a[0], a[1]) : make_uint4(a[0], a[1], a[2], a[3]);
  }
}

__device__ __forceinline__ void prep_gate(const Params& p, uint32_t sb, int b, int w, int lane) {
  uint2 gw[5], x[4][5];
#pragma unroll
  for (int j = 0; j < 5; j++) gw[j] = ldg64(reinterpret_cast<const uint2*>(p.gate_w) + lane + 32 * j);
#pragma unroll
  for (int i = 0; i < 4; i++)
#pragma unroll
    for (int j = 0; j < 5; j++)
      x[i][j] = ldg64(reinterpret_cast<const uint2*>(p.q) + (16 * b + 4 * w + i) * (DIM / 4) + lane + 32 * j);
  float s[4];
#pragma unroll
  for (int i = 0; i < 4; i++) {
    s[i] = 0.f;
#pragma unroll
    for (int j = 0; j < 5; j++) {
      const uint32_t m0 = bmul(x[i][j].x, gw[j].x), m1 = bmul(x[i][j].y, gw[j].y);
      s[i] += (bf_lo(m0) + bf_hi(m0)) + (bf_lo(m1) + bf_hi(m1));
    }
  }
  const bool h = lane & 16, q = lane & 8;
  const float a = (h ? s[2] : s[0]) + __shfl_xor_sync(0xffffffffu, h ? s[0] : s[2], 16);
  const float c = (h ? s[3] : s[1]) + __shfl_xor_sync(0xffffffffu, h ? s[1] : s[3], 16);
  float z = (q ? c : a) + __shfl_xor_sync(0xffffffffu, q ? a : c, 8);
#pragma unroll
  for (int o = 4; o > 0; o >>= 1) z += __shfl_xor_sync(0xffffffffu, z, o);
  z = bf_lo(pack2(z, 0.f));
  z = bf_lo(pack2(__fdividef(1.f, 1.f + __expf(-z)), 0.f));
  mbar_wait(sb + OFF_BAR + 8 * B_S3, 0);
  if ((lane & 7) == 0) asm volatile("st.shared.f32 [%0], %1;" ::"r"(sb + OFF_GATE + 64 * (b & 7) + 16 * w + (lane >> 1)), "f"(z) : "memory");
  fence_async_smem();
}

__device__ __forceinline__ uint32_t bmax(uint32_t a, uint32_t b) {
  uint32_t d;
  asm("max.bf16x2 %0, %1, %2;" : "=r"(d) : "r"(a), "r"(b));
  return d;
}
__device__ __forceinline__ void softmax_two(const float (&l)[2][2], uint32_t& p0, uint32_t& p1) {
  constexpr float kScale = 0.22360679774997896f, kLog2e = 1.4426950408889634f;
  const uint32_t r0 = pack2(l[0][0], l[1][0]), r1 = pack2(l[0][1], l[1][1]);
  const uint32_t x0 = pack2(bf_lo(r0) * kScale, bf_hi(r0) * kScale), x1 = pack2(bf_lo(r1) * kScale, bf_hi(r1) * kScale);
  uint32_t m = bmax(x0, x1);
  m = bmax(m, __shfl_xor_sync(0xffffffffu, m, 1));
  m = bmax(m, __shfl_xor_sync(0xffffffffu, m, 2));
  const float m0 = bf_lo(m) * kLog2e, m1 = bf_hi(m) * kLog2e;
  p0 = pack2(ex2(bf_lo(x0) * kLog2e - m0), ex2(bf_lo(x1) * kLog2e - m0));
  p1 = pack2(ex2(bf_hi(x0) * kLog2e - m1), ex2(bf_hi(x1) * kLog2e - m1));
}

__device__ __forceinline__ void halo_read(uint32_t (&kpv)[10], uint32_t (&vpv)[10], uint32_t (&tg)[7], const uint4* hp) {
#pragma unroll
  for (int j = 0; j < 7; j++) {
    uint32_t x0, x1, x2;
    asm volatile("ld.relaxed.gpu.global.v4.u32 {%0, %1, %2, %3}, [%4];"
                 : "=r"(x0), "=r"(x1), "=r"(x2), "=r"(tg[j]) : "l"(hp + 32 * j) : "memory");
    if (j < 4) kpv[3 * j] = x0; else vpv[3 * j - 10] = x0;
    if (j < 3) kpv[3 * j + 1] = x1; else vpv[3 * j - 9] = x1;
    if (j < 3) kpv[3 * j + 2] = x2; else if (j < 6) vpv[3 * j - 8] = x2;
  }
}

template <int ROT>
__device__ __forceinline__ void pack_qkv(const float* acc, uint32_t (&qlo)[10], uint32_t (&qhi)[10], uint32_t (&klo)[10],
                                         uint32_t (&khi)[10], uint32_t (&vlo)[10], uint32_t (&vhi)[10]) {
#pragma unroll
  for (int j = 0; j < 10; j++) {
    const int x = (j + ROT) % 10, tq = x < 8 ? x : 16 + x, tk = x < 8 ? 8 + x : 18 + x, tv = x < 8 ? 16 + x : 20 + x;
    khi[j] = pack2(acc[4 * tk + 2], acc[4 * tk + 3]);
    vhi[j] = movm(pack2(acc[4 * tv + 2], acc[4 * tv + 3]));
    qlo[j] = pack2(acc[4 * tq], acc[4 * tq + 1]);
    qhi[j] = pack2(acc[4 * tq + 2], acc[4 * tq + 3]);
    klo[j] = pack2(acc[4 * tk], acc[4 * tk + 1]);
    vlo[j] = pack2(acc[4 * tv], acc[4 * tv + 1]);
    asm volatile("" : "+r"(khi[j]), "+r"(qlo[j]), "+r"(qhi[j]), "+r"(klo[j]), "+r"(vlo[j]));
  }
}

template <int ROT> __device__ __forceinline__ void halo_send(const float* acc, uint4* ho, uint32_t tag) {
#pragma unroll
  for (int j = 0; j < 7; j++) {
    uint32_t x[3];
#pragma unroll
    for (int e = 0; e < 3; e++) {
      const int i = 3 * j + e, y = (i % 10 + ROT) % 10, tk = y < 8 ? 8 + y : 18 + y, tv = y < 8 ? 16 + y : 20 + y;
      x[e] = i < 10 ? pack2(acc[4 * tk + 2], acc[4 * tk + 3]) : i < 20 ? movm(pack2(acc[4 * tv + 2], acc[4 * tv + 3])) : 0u;
    }
    asm volatile("st.relaxed.gpu.global.v4.u32 [%0], {%1, %2, %3, %4};" ::"l"(ho + 32 * j), "r"(x[0]), "r"(x[1]), "r"(x[2]), "r"(tag) : "memory");
  }
}

__device__ __forceinline__ void attention(float* acc, uint32_t sb, int b, int par, int w, int lane, uint32_t tag) {
  const int g = lane >> 2, t = lane & 3;
  uint32_t klo[10], khi[10], vlo[10], vhi[10], qlo[10], qhi[10], kpv[10], vpv[10];
  if (w == 3 && b < NCTA - 8) {
    uint4* ho = g_halo + (b * 2 + par) * 224 + lane;
    if (tail_first(b & 7)) halo_send<8>(acc, ho, tag);
    else halo_send<0>(acc, ho, tag);
    TSIF(par == 0, 76);
    pin<120>(acc);
  }
  if (tail_first(b & 7)) pack_qkv<8>(acc, qlo, qhi, klo, khi, vlo, vhi);
  else pack_qkv<0>(acc, qlo, qhi, klo, khi, vlo, vhi);
  const uint32_t xa = sb + OFF_KVX + (par * 3) * 2560 + lane * 16;
  if (w < 3) {
    sts128(xa + w * 2560, khi[0], khi[1], khi[2], khi[3]);
    sts128(xa + w * 2560 + 512, khi[4], khi[5], khi[6], khi[7]);
    sts128(xa + w * 2560 + 1024, khi[8], khi[9], vhi[0], vhi[1]);
    sts128(xa + w * 2560 + 1536, vhi[2], vhi[3], vhi[4], vhi[5]);
    sts128(xa + w * 2560 + 2048, vhi[6], vhi[7], vhi[8], vhi[9]);
  }
  TSIF(par == 0 && w == 1, 64);
#pragma unroll
  for (int j = 0; j < 10; j++) vlo[j] = movm(vlo[j]);
  const bool far0 = 2 * t > g, far1 = 2 * t + 1 > g;
  const uint32_t mfar = (far0 ? 0x0000FFFFu : 0u) | (far1 ? 0xFFFF0000u : 0u);
  float slo[4][2], lg[2][2];
  uint32_t phi[4], plo[4], qml[4], qmh[4];
#pragma unroll
  for (int h = 0; h < 4; h++) {
    const int f = h == 0 ? 0 : h == 1 ? 3 : h == 2 ? 5 : 8, hf = h < 2 ? 2 : 7;
    const bool mine = (h & 1) ? t >= 2 : t < 2;
    qml[h] = mine ? qlo[hf] : 0u;
    qmh[h] = mine ? qhi[hf] : 0u;
    float a[4] = {0.f, 0.f, 0.f, 0.f}, c[4] = {0.f, 0.f, 0.f, 0.f};
    mma16816(a, qlo[f], qhi[f], qlo[f + 1], qhi[f + 1], klo[f], klo[f + 1]);
    mma16816(c, qlo[f], qhi[f], qlo[f + 1], qhi[f + 1], khi[f], khi[f + 1]);
    mma1688(a, qml[h], qmh[h], klo[hf]);
    mma1688(c, qml[h], qmh[h], khi[hf]);
    slo[h][0] = a[0];
    slo[h][1] = a[1];
    lg[h & 1][0] = far0 ? a[2] : c[2];
    lg[h & 1][1] = far1 ? a[3] : c[3];
    if (h & 1) softmax_two(lg, phi[h - 1], phi[h]);
  }
  TSIF(par == 0 && w == 1, 65);
  wg_sync(1 + par);
  TSIF(par == 0 && w == 1, 66);
  const bool nohist = (w == 0) && (b < 8);
  const uint4* hp = g_halo + ((b - 8) * 2 + par) * 224 + lane;
  uint32_t tg[7];
  if (w > 0) {
    const uint4 v0 = lds128(xa + (w - 1) * 2560), v1 = lds128(xa + (w - 1) * 2560 + 512), v2 = lds128(xa + (w - 1) * 2560 + 1024);
    const uint4 v3 = lds128(xa + (w - 1) * 2560 + 1536), v4 = lds128(xa + (w - 1) * 2560 + 2048);
    kpv[0] = v0.x; kpv[1] = v0.y; kpv[2] = v0.z; kpv[3] = v0.w; kpv[4] = v1.x; kpv[5] = v1.y; kpv[6] = v1.z; kpv[7] = v1.w;
    kpv[8] = v2.x; kpv[9] = v2.y; vpv[0] = v2.z; vpv[1] = v2.w; vpv[2] = v3.x; vpv[3] = v3.y; vpv[4] = v3.z; vpv[5] = v3.w;
    vpv[6] = v4.x; vpv[7] = v4.y; vpv[8] = v4.z; vpv[9] = v4.w;
  } else if (nohist) {
#pragma unroll
    for (int j = 0; j < 10; j++) kpv[j] = vpv[j] = 0u;
  } else {
    TSIF(par == 0, 77);
    halo_read(kpv, vpv, tg, hp);
  }
  if (w == 0 && !nohist) {
    int spins = 0;
    while (true) {
      bool ok = true;
#pragma unroll
      for (int j = 0; j < 7; j++) ok = ok && tg[j] == tag;
      if (__all_sync(0xffffffffu, ok) || ++spins > SPIN_LIMIT) break;
      halo_read(kpv, vpv, tg, hp);
    }
    TSIF(par == 0, 79);
  }
#pragma unroll
  for (int h = 0; h < 4; h++) {
    const int f = h == 0 ? 0 : h == 1 ? 3 : h == 2 ? 5 : 8, hf = h < 2 ? 2 : 7;
    float a[4] = {0.f, 0.f, 0.f, 0.f};
    mma16816(a, qlo[f], qhi[f], qlo[f + 1], qhi[f + 1], kpv[f], kpv[f + 1]);
    mma1688(a, qml[h], qmh[h], kpv[hf]);
    const float ninf = __int_as_float(0xff800000);
    lg[h & 1][0] = far0 ? (nohist ? ninf : a[0]) : slo[h][0];
    lg[h & 1][1] = far1 ? (nohist ? ninf : a[1]) : slo[h][1];
    if (h & 1) softmax_two(lg, plo[h - 1], plo[h]);
  }
  TSIF(par == 0 && w <= 1, 67 + w);
  uint32_t ov[20];
#pragma unroll
  for (int hp = 0; hp < 2; hp++) {
    const int hf = hp ? 7 : 2;
    float sh[4] = {0.f, 0.f, 0.f, 0.f}, i0 = 0.f, i1 = 0.f;
#pragma unroll
    for (int e = 0; e < 2; e++) {
      const int h = 2 * hp + e, f = h == 0 ? 0 : h == 1 ? 3 : h == 2 ? 5 : 8;
      const uint32_t a0 = plo[h] & mfar, a2 = plo[h] & ~mfar, a3 = phi[h] & mfar, c1 = phi[h] & ~mfar;
      float sum[4] = {0.f, 0.f, 0.f, 0.f};
      mma1688(sum, plo[h], phi[h], 0x3F803F80u);
      const float r0 = rcp(sum[0]), r1 = rcp(sum[2]);
#pragma unroll
      for (int j = f; j < f + 2; j++) {
        float o[4] = {0.f, 0.f, 0.f, 0.f};
        mma16816(o, a0, 0u, a2, a3, vpv[j], vlo[j]);
        mma1688(o, 0u, c1, vhi[j]);
        ov[2 * j] = pack2(o[0] * r0, o[1] * r0);
        ov[2 * j + 1] = pack2(o[2] * r1, o[3] * r1);
      }
      const bool mine = e ? g >= 4 : g < 4;
      mma16816(sh, a0, 0u, a2, a3, mine ? vpv[hf] : 0u, mine ? vlo[hf] : 0u);
      mma1688(sh, 0u, c1, mine ? vhi[hf] : 0u);
      if (e == 0 || t >= 2) {
        i0 = r0;
        i1 = r1;
      }
    }
    ov[2 * hf] = pack2(sh[0] * i0, sh[1] * i0);
    ov[2 * hf + 1] = pack2(sh[2] * i1, sh[3] * i1);
  }
  TS(32 + 4 * par + w);
  mbar_wait(sb + OFF_BAR + 8 * B_P1, 0);
  const uint32_t oa = sb + OFF_OA + (lane >> 4) * 2048 + (32 * w + 2 * (lane & 15) + par) * 16;
#pragma unroll
  for (int j = 0; j < 5; j++) stsm4(oa + 4096 * j, ov + 4 * j);
  TSIF(par == 0 && w == 0, 120);
  fence_async_smem();
  TSIF(par == 0 && w == 0, 121);
  __syncwarp();
  if (lane == 0) mbar_arrive(sb + OFF_BAR + 8 * B_ATTN);
  TSM(w == 0 || w == 2, 122 + par + (w == 2 ? 3 : 0));
}

struct Maps {
  CUtensorMap x, wm, wt, k, v, y, wo, qm, qt, om, ot, yl, ol, wh;
};

__device__ __forceinline__ void load_stage(uint32_t sb, int kb, int b, const Maps& m) {
  const uint32_t st = sb + (kb & 3) * STAGE_BYTES, bar = sb + OFF_BAR + 8 * (B_FULL1 + (kb & 3));
  const int r = b >> 3, hg = b & 7, slab = kb - KV_KB;
  const bool kv = slab >= 0 && slab < 5;
  const uint32_t kbar = sb + OFF_BAR + 8 * (B_KV + slab), dst = sb + OFF_KVS + slab * KVS_BYTES;
  mbar_expect_tx(bar, STAGE_BYTES);
  if (kv) mbar_expect_tx(kbar, KVS_BYTES);
  tma_3d(st, &m.x, 64 * kb, 64 * r, 0, bar);
  tma_3d(st + ST_W, &m.wm, 80 * hg + (tail_first(hg) ? 16 : 0), 64 * kb, 0, bar);
  tma_3d(st + ST_WT, &m.wt, 80 * hg + (tail_first(hg) ? 0 : 64), 64 * kb, 0, bar);
  if (kv) tma_3d(dst, &m.k, 0, 32 * (b >> 1) - 3, 2 * slab + (b & 1), kbar);
  if (kv) tma_3d(dst + KVS_V, &m.v, 0, 32 * (b >> 1), 2 * slab + (b & 1), kbar);
}

__global__ void __launch_bounds__(NTHR, 1) fused_kernel(const __grid_constant__ Maps m, const Params p) {
  extern __shared__ __align__(1024) uint8_t smem[];
  const uint32_t sb = (uint32_t)__cvta_generic_to_shared(smem);
  const uint32_t bars = sb + OFF_BAR;
  const int tid = threadIdx.x, lane = tid & 31;
  int b = blockIdx.x;
  b = (((b & 63) >> 3) * 2 + (b & 1)) * 8 + (((b < 64 ? 0x6521 : 0x7430) >> (4 * ((b >> 1) & 3))) & 7);
  const int r = b >> 3, hg = b & 7;

  if (tid == T_ISSUE) {
    TSM(true, 0);
#pragma unroll
    for (int i = 0; i < 4; i++) mbar_init(bars + 8 * (B_F0 + i), 1);
    fence_async_smem();
#pragma unroll
    for (int i = 0; i < 4; i++) {
      mbar_expect_tx(bars + 8 * (B_F0 + i), (i ? 0 : ST_W) + 6144);
      if (i == 0) tma_3d(sb, &m.x, 0, 64 * r, 0, bars + 8 * B_F0);
      tma_3d(sb + ST_W + 6144 * i, &m.wh, 80 * hg + (tail_first(hg) ? 16 : 0), 16 * i, 0, bars + 8 * (B_F0 + i));
    }
#pragma unroll
    for (int i = 0; i < 4; i++) mbar_init(bars + 8 * (B_FULL1 + i), 1);
    fence_async_smem();
    mbar_expect_tx(bars + 8 * B_FULL1, STAGE_BYTES - ST_WT);
    tma_3d(sb + ST_WT, &m.wt, 80 * hg + (tail_first(hg) ? 0 : 64), 0, 0, bars + 8 * B_FULL1);
    load_stage(sb, 1, b, m);
  } else if (tid == T_INIT) {
#pragma unroll
    for (int i = 0; i < B_F0; i++) mbar_init(bars + 8 * i, i < B_GATE ? 8 : i < B_CVD ? 4 : i == B_CVD ? 20 : 1);
    fence_async_smem();
  }
  const int warp = __shfl_sync(0xffffffffu, tid >> 5, 0), wg = warp >> 2, w = warp & 3;
  __syncthreads();

  if (wg == 3) {
    asm volatile("setmaxnreg.dec.sync.aligned.u32 56;");
    if (w == 0) {
      if (lane == 0) {
#pragma unroll 1
        for (int kb = 2; kb < 10; kb++) {
          if (kb >= 4) mbar_wait(bars + 8 * (kb == 7 ? B_E3 : B_EMPTY1 + (kb & 3)), (kb >> 3) & 1);
          TSIF(kb >= 4, 44 + kb);
          load_stage(sb, kb, b, m);
          TSIF(kb == 3, 60);
          if (kb == 9) mbar_arrive(bars + 8 * B_LAST);
        }
        mbar_wait(bars + 8 * B_WOP, 0);
        mbar_wait(bars + 8 * B_EPOCH, 0);
        flag_wait(g_cnt + C_W + 32 * hg, (lds32(sb + OFF_EPOCH) + 1) * 16);
        TS(30);
#pragma unroll 1
        for (int j = 0; j < 8; j++) {
          if (j >= 6) mbar_wait(bars + 8 * (B_EMPTY2 + j - 6), 0);
          if (j == 4) mbar_wait(bars + 8 * B_ORB, 0);
          TSIF(j >= 6, 100 + j);
          mbar_expect_tx(bars + 8 * (B_FULL2 + j), j == 0 ? WO_BYTES : j == 5 ? O_BYTES + WO_BYTES + 512 : O_BYTES + WO_BYTES);
          bulk_load(sb + off_w(j), g_WO + (hg * 8 + step_src(hg, j)) * 800, WO_BYTES, bars + 8 * (B_FULL2 + j));
        }
        mbar_wait(bars + 8 * (B_EMPTY2 + 3), 0);
        mbar_expect_tx(bars + 8 * B_QF, O_BYTES);
        tma_2d(sb + OFF_QS, &m.qm, 80 * hg, 128 * r, bars + 8 * B_QF);
        tma_2d(sb + OFF_QT, &m.qt, 80 * hg + 64, 128 * r, bars + 8 * B_QF);
      }
    } else if (w == 1) {
      unsigned epoch = 0;
      if (lane == 0) {
        epoch = atomicAdd(g_cnt + C_LAUNCH, 1u) / NCTA;
        asm volatile("st.shared.u32 [%0], %1;" ::"r"(sb + OFF_EPOCH), "r"(epoch) : "memory");
        mbar_arrive(bars + 8 * B_EPOCH);
        mbar_wait(bars + 8 * B_KVD, 0);
        mbar_expect_tx(bars + 8 * B_HB, 5 * 4096);
#pragma unroll 1
        for (int c = 0; c < 5; c++) {
          if (c == 3) mbar_wait(bars + 8 * B_S3, 0);
          bulk_load(sb + off_ch(c) + U_BYTES, p.ssm_k + (5 * b + c) * SEQ, 4096, bars + 8 * B_HB);
        }
#pragma unroll
        for (int c = 0; c < 4; c++) mbar_expect_tx(bars + 8 * (B_U + c), c < 3 ? U_BYTES : 2 * U_BYTES);
        const uint4* usrc = g_U + 5 * b * U_PITCH;
        mbar_wait(bars + 8 * B_USIG, 0);
        flag_wait(g_cnt + C_PREP + 32 * (b & 15), (epoch + 1) * NCTA);
        TS(23);
#pragma unroll
        for (int c = 0; c < 5; c++) {
          if (c == 3) mbar_wait(bars + 8 * (B_U + 2), 0);
          bulk_load(sb + off_ch(c), usrc + c * U_PITCH, U_BYTES, bars + 8 * (B_U + (c < 3 ? c : 3)));
          TSIF(c == 0 || c == 4, 116 + (c >> 2));
        }
      }
      epoch = __shfl_sync(0xffffffffu, epoch, 0);
      if (lane < 8) {
        const int src = (b & ~7) | step_src(hg, lane);
        mbar_wait(bars + 8 * B_ATTN, 0);
        TS(20);
        bool seen = false;
#pragma unroll 1
        for (int spins = 0; spins < SPIN_LIMIT; spins++) {
          const bool now = !seen && (int)(flag_read(g_cnt + C_O + 32 * src) - (epoch + 1)) >= 0;
          if (now && lane >= 1 && lane < 4) bulk_load(sb + off_o(lane), g_O + src * 1280, O_BYTES, bars + 8 * (B_FULL2 + lane));
          seen = seen || now;
          if (__all_sync(0xff, seen)) break;
        }
        TS(21);
        if (lane == 5) bulk_load(sb + OFF_GATE, g_gate + 128 * r, 512, bars + 8 * (B_FULL2 + 5));
#pragma unroll 1
        for (int j = 4; j < 8; j++) {
          if (lane == j) {
            mbar_wait(bars + 8 * (j < 6 ? B_C34 : B_EMPTY2 + j - 6), 0);
            bulk_load(sb + off_o(j), g_O + src * 1280, O_BYTES, bars + 8 * (B_FULL2 + j));
          }
          __syncwarp(0xff);
        }
        TS(22);
      }
    } else if (w == 2) {
      mbar_wait(bars + 8 * B_PREP, 0);
      flag_signal(g_cnt + C_PREP, 16, lane);
      TS(25);
      if (lane == 0) {
        mbar_arrive(bars + 8 * B_USIG);
        mbar_expect_tx(bars + 8 * B_ORB, O_BYTES / 4 + 64);
        mbar_wait(bars + 8 * B_GATE, 0);
        publish(g_gate + 16 * b, sb + OFF_GATE + 64 * hg, 64);
        bulk_load(sb + OFF_GATE + 64 * hg, g_gate + 16 * b, 64, bars + 8 * B_ORB);
        mbar_wait(bars + 8 * B_ATTN, 0);
        publish(g_O + b * 1280, sb + OFF_OA, O_BYTES);
        tma_2d(sb + OFF_KVX + 10240, &m.ol, 48, b * 160, bars + 8 * B_ORB);
        TS(74);
        mbar_wait(bars + 8 * B_ORB, 0);
        flag_bump(g_cnt + C_O + 32 * b);
        TS(26);
      }
    } else {
      if (lane == 0) {
        uint4* dst = g_WO + (hg * 8 + (r >> 1)) * 800 + (r & 1) * 80;
        mbar_wait(bars + 8 * B_S3, 0);
        asm volatile("cp.async.bulk.prefetch.L2.global [%0], 6400;" ::"l"(p.wo + b * 3200) : "memory");
        mbar_wait(bars + 8 * B_P1, 0);
        mbar_wait(bars + 8 * WB_TRIG, 0);
        mbar_expect_tx(bars + 8 * B_WST, WO_BYTES / 2);
        tma_3d(sb + OFF_WA, &m.wo, 0, 40 * r, 5 * hg, bars + 8 * B_WST);
        mbar_wait(bars + 8 * B_WST, 0);
#pragma unroll 1
        for (int n = 0; n < 5; n++) bulk_store(dst + 160 * n, sb + OFF_WA + 1280 * n, 1280);
        bulk_wait_read();
        mbar_expect_tx(bars + 8 * B_WST, WO_BYTES / 2);
#pragma unroll 1
        for (int n = 0; n < 5; n++) bulk_load(sb + OFF_WA + 1280 * n, dst + 160 * n, 1280, bars + 8 * B_WST);
        mbar_wait(bars + 8 * B_WST, 1);
        flag_bump(g_cnt + C_W + 32 * hg);
        mbar_arrive(bars + 8 * B_WOP);
        TS(71);
        mbar_expect_tx(bars + 8 * B_C34, 3 * (U_BYTES / 4));
        mbar_expect_tx(bars + 8 * B_YRB, 2 * (U_BYTES / 4));
#pragma unroll 1
        for (int c = 0; c < 5; c++) {
          mbar_wait(bars + 8 * (B_YST + c), 0);
          publish(g_U + (5 * b + c) * U_PITCH, sb + off_ch(c), U_BYTES);
          tma_2d(sb + off_ch(c), &m.yl, 48, (5 * b + c) * (U_PITCH / 8), bars + 8 * (c < 3 ? B_C34 : B_YRB));
        }
        TS(75);
        mbar_wait(bars + 8 * B_C34, 0);
        mbar_wait(bars + 8 * B_YRB, 0);
        flag_bump(g_cnt + C_Y + 32 * (b >> 4));
        TS(27);
        mbar_expect_tx(bars + 8 * B_YFULL, 20480);
        flag_wait(g_cnt + C_Y + 32 * hg, (lds32(sb + OFF_EPOCH) + 1) * 16);
        TS(24);
        tma_2d(sb + OFF_YT, &m.y, 128 * r, 80 * hg, bars + 8 * B_YFULL);
        tma_2d(sb + OFF_YT + 10240, &m.y, 128 * r + 64, 80 * hg, bars + 8 * B_YFULL);
      }
    }
  } else {
    asm volatile("setmaxnreg.inc.sync.aligned.u32 152;");
    if (wg < 2) {
      float acc[120];
#pragma unroll
      for (int i = 0; i < 120; i++) acc[i] = 0.f;
      const uint32_t da = desc_lo(sb + wg * 8192, 16), db = desc_lo(sb + ST_W, 8192), dc = desc_lo(sb + ST_WT, 2048);
#pragma unroll
      for (int k = 0; k < 4; k++) {
        mbar_wait(bars + 8 * (B_F0 + k), 0);
        TSIF(w == 0 && wg == 0 && k == 0, 1);
        wg_fence();
        WgSST<192>::mma<HI_SW128, HI_SW128>(acc, da + 2 * k, desc_lo(sb + ST_W, 2048) + 384 * k, 1);
        wg_commit();
      }
      mbar_wait(bars + 8 * B_FULL1, 0);
      wg_fence();
#pragma unroll
      for (int k = 0; k < 4; k++) WgSST<48>::mma<HI_SW128, HI_SW32>(acc + 96, da + 2 * k, dc + 32 * k, 1);
      wg_commit();
#pragma unroll 1
      for (int kb = 1; kb < 10; kb++) {
        mbar_wait(bars + 8 * (B_FULL1 + (kb & 3)), (kb >> 2) & 1);
        const uint32_t so = (kb & 3) * (STAGE_BYTES >> 4);
        wg_fence();
#pragma unroll
        for (int k = 0; k < 4; k++) {
          WgSST<192>::mma<HI_SW128, HI_SW128>(acc, da + so + 2 * k, db + so + 128 * k, 1);
          WgSST<48>::mma<HI_SW128, HI_SW32>(acc + 96, da + so + 2 * k, dc + so + 32 * k, 1);
        }
        wg_commit();
        wg_wait<1>();
        if (lane == 0) mbar_arrive(bars + 8 * (kb == 4 ? B_E3 : B_EMPTY1 + ((kb - 1) & 3)));
      }
      mbar_wait(bars + 8 * B_EPOCH, 0);
      const uint32_t tag = lds32(sb + OFF_EPOCH) + 1;
      mbar_wait(bars + 8 * B_S3, 0);
      wg_wait<0>();
      pin<120>(acc);
      if (lane == 0) mbar_arrive(bars + 8 * B_P1);
      TSM(w == 0, 3 + wg);
      attention(acc, sb, b, wg, w, lane, tag);
    } else {
      const int tw = tid & 127, chl = 64 * (b & 1) + 8 * w + (lane >> 2);
      uint4* up = g_U + chl * U_PITCH + ((4 * (b >> 1) + (lane & 3)) ^ ((b >> 2) & 1));
      uint2 sw[10];
      uint32_t dv = 0;
      if (lane < 5) dv = __ldg(reinterpret_cast<const unsigned short*>(p.ssm_D) + 5 * b + lane);
#pragma unroll
      for (int i = 0; i < 10; i++) sw[i] = ldg64(reinterpret_cast<const uint2*>(p.shift_k) + chl + 128 * (i >> 1) + 32 * (i & 1));
      uint32_t tab[12];
      uint32_t tt[2];
      fft_tables(tab, tw);
      fft_twiddles(tt, tw);
      uint4 res[10];
#pragma unroll
      for (int i = 0; i < 10; i++) res[i] = make_uint4(0, 0, 0, 0);
#pragma unroll 1
      for (int slab = 0; slab < 5; slab++) {
#pragma unroll
        for (int i = 0; i < 8; i++) res[i] = res[i + 2];
        prep_slab(res + 8, sw, sb, slab, w, lane);
        if (slab >= U_FROM && slab < U_TO) {
          up[128 * slab * U_PITCH] = res[8];
          up[(128 * slab + 32) * U_PITCH] = res[9];
        }
        TSIF(w == 0, 99 + 4 * slab);
#pragma unroll
        for (int i = 0; i < 8; i++) sw[i] = sw[i + 2];
      }
      TSIF(w == 0, 28);
      __syncwarp();
      if (lane == 0) mbar_arrive(bars + 8 * B_KVD + ((res[8].x ^ res[9].x) & p.zero));
      mbar_wait(bars + 8 * B_KVD, 0);
      fft_tables_store(tab, sb, tw);
      mbar_wait(bars + 8 * B_LAST, 0);
#pragma unroll
      for (int i = 0; i < 10; i++)
        if (i / 2 < U_FROM || i / 2 >= U_TO) up[(128 * (i >> 1) + 32 * (i & 1)) * U_PITCH] = res[i];
      __syncwarp();
      if (lane == 0) mbar_arrive(bars + 8 * B_PREP);
      TSIF(w == 0, 5);
      mbar_wait(bars + 8 * B_LAST, 0);
      prep_gate(p, sb, b, w, lane);
      __syncwarp();
      if (lane == 0) mbar_arrive(bars + 8 * B_GATE);
      TSIF(w == 0, 72);
      mbar_wait(bars + 8 * B_HB, 0);
      TSIF(w == 0, 2);
      const uint32_t ha = sb + U_BYTES + ((tw >> 3) * 16 + 8 + (tw & 7)) * 16;
      uint4 hv[5];
#pragma unroll
      for (int c = 0; c < 5; c++) hv[c] = lds128(ha + off_ch(c));
      __syncwarp();
#pragma unroll
      for (int c = 0; c < 5; c++) sts128((ha ^ 16) + off_ch(c), hv[c].x, hv[c].y, hv[c].z, hv[c].w);
      asm volatile("st.shared.v2.u32 [%0], {%1, %2};" ::"r"(sb + OFF_TT + 8 * tw), "r"(tt[0]), "r"(tt[1]) : "memory");
      if (tw < 5) asm volatile("st.shared.f32 [%0], %1;" ::"r"(sb + OFF_D + 4 * tw), "f"(bf_lo(dv) * 0.125f) : "memory");
      fence_async_smem();
      __syncwarp();
      if (lane == 0) mbar_arrive(bars + 8 * B_HA);
      TSIF(w == 0, 6);
    }

    FftConst fc;
    TSM(w == 0 && wg == 0, 104);
    mbar_wait(bars + 8 * B_HA, 0);
    fft_matrices(fc, sb, w, lane);
    TSM(w == 0 && wg == 0, 105);
    TSM(w == 0 && wg == 2, 124);
#pragma unroll 1
    for (uint32_t tasks = wg == 0 ? TASK0 : wg == 1 ? TASK1 : TASK2; tasks; tasks >>= 4) {
      const int c = (tasks & 7) - 1;
      conv_channel(fc, sb, c, wg, w, lane);
      if (lane == 0) mbar_arrive(bars + 8 * (B_YST + c));
      TSM(w == 0, 10 + c);
    }

    if (wg != 1) {
      const int wg = warp >> 3;
      const int g = lane >> 2;
      float acc[40];
#pragma unroll
      for (int i = 0; i < 40; i++) acc[i] = 0.f;
      const uint32_t da = desc_lo(sb + wg * 1024, 2048), db = desc_lo(sb, 2560);
      mbar_wait(bars + 8 * B_ORB, 0);
      mbar_wait(bars + 8 * B_FULL2, 0);
      TSM(w == 0, 15 + wg);
#pragma unroll 1
      for (int j = 0; j < 8; j++) {
        if (j == 1 - wg) mbar_wait(bars + 8 * B_CVD, 0);
        mbar_wait(bars + 8 * (B_FULL2 + j), 0);
        TSM(w == 0 && wg == 0, 44 + (j < 4 ? j : j + 6));
        const uint32_t oa = da + (off_o(j) >> 4), ob = db + (off_w(j) >> 4);
        wg_fence();
#pragma unroll
        for (int k = 0; k < 5; k++) WgSST<80>::mma<HI_NONE, HI_SW32>(acc, oa + 256 * k, ob + 32 * k, 1);
        wg_commit();
        wg_wait<1>();
        if (j >= 1 && j <= 4 && lane == 0) mbar_arrive(bars + 8 * (B_EMPTY2 + j - 1));
      }
      TSIF(w == 0 && wg == 0, 113);
      const int tr = 64 * wg + 16 * w + (lane & 15);
      const uint32_t fm = sb + OFF_QS + tr * 128, fx = (lane >> 4) ^ (tr & 7);
      const uint32_t ft = sb + OFF_QT + tr * 32 + (((lane >> 4) ^ (tr >> 2)) & 1) * 16;
      const float g0 = __uint_as_float(lds32(sb + OFF_GATE + (64 * wg + 16 * w + g) * 4));
      const float g1 = __uint_as_float(lds32(sb + OFF_GATE + (64 * wg + 16 * w + 8 + g) * 4));
      const uint32_t ga = pack2(g0, g0), gb = pack2(g1, g1);
      const uint32_t na = pack2(1.f - g0, 1.f - g0), nb = pack2(1.f - g1, 1.f - g1);

      uint32_t qf[20];
      mbar_wait(bars + 8 * B_QF, 0);
      TSM(w == 0 && wg == 0, 99);
#pragma unroll
      for (int j = 0; j < 5; j++) ldsm4(qf + 4 * j, j < 4 ? fm + ((fx ^ (2 * j)) << 4) : ft);
#pragma unroll
      for (int i = 0; i < 20; i++) {
        qf[i] = bmul((i & 1) ? gb : ga, qf[i]);
        asm volatile("" : "+r"(qf[i]));
      }

      wg_wait<0>();
      pin<40>(acc);
      TSM(w == 0, 17 + wg);
      uint32_t pb[20];
#pragma unroll
      for (int j = 0; j < 10; j++) {
        pb[2 * j] = bmul(na, pack2(acc[4 * j], acc[4 * j + 1]));
        pb[2 * j + 1] = bmul(nb, pack2(acc[4 * j + 2], acc[4 * j + 3]));
        asm volatile("" : "+r"(pb[2 * j]), "+r"(pb[2 * j + 1]));
      }
      const uint32_t ya = sb + OFF_YT + wg * 10240 + ((lane >> 4) * 8 + (lane & 7)) * 128 +
                          (((2 * w + (((lane >> 3) & 1) ^ wg)) ^ (lane & 7)) << 4);
      mbar_wait(bars + 8 * B_YFULL, 0);
      TSM(w == 0 && wg == 0, 19);
#pragma unroll
      for (int j = 0; j < 5; j++) {
        uint32_t y[4];
        ldsm4t(y, ya + 2048 * j);
#pragma unroll
        for (int i = 0; i < 4; i++)
          qf[4 * j + i] = bfma(qf[4 * j + i], y[i], pb[4 * j + i]);
      }
#pragma unroll
      for (int j = 0; j < 5; j++) stsm4(j < 4 ? fm + ((fx ^ (2 * j)) << 4) : ft, qf + 4 * j);
      fence_async_smem();
      __syncwarp();
      if (lane == 0) {
        const int row = 64 * wg + 16 * w;
        asm volatile("cp.async.bulk.tensor.2d.global.shared::cta.bulk_group [%0, {%2, %3}], [%1];"
                     ::"l"(&m.om), "r"(sb + OFF_QS + row * 128), "r"(80 * hg), "r"(128 * r + row) : "memory");
        asm volatile("cp.async.bulk.tensor.2d.global.shared::cta.bulk_group [%0, {%2, %3}], [%1];"
                     ::"l"(&m.ot), "r"(sb + OFF_QT + row * 32), "r"(80 * hg + 64), "r"(128 * r + row) : "memory");
        asm volatile("cp.async.bulk.commit_group;\ncp.async.bulk.wait_group.read 0;" ::: "memory");
      }
      TSM(w == 0 || w == 3, 40 + 2 * wg + (w & 1));
    }
  }
}

typedef CUresult (*EncodeFn)(CUtensorMap*, CUtensorMapDataType, cuuint32_t, void*, const cuuint64_t*, const cuuint64_t*,
                             const cuuint32_t*, const cuuint32_t*, CUtensorMapInterleave, CUtensorMapSwizzle,
                             CUtensorMapL2promotion, CUtensorMapFloatOOBfill);

void encode(EncodeFn fn, CUtensorMap* tm, const void* base, int rank, const cuuint64_t* dims, const cuuint64_t* strides,
            const cuuint32_t* box, CUtensorMapSwizzle swz) {
  const cuuint32_t ones[3] = {1, 1, 1};
  fn(tm, CU_TENSOR_MAP_DATA_TYPE_BFLOAT16, rank, const_cast<void*>(base), dims, strides, box, ones,
     CU_TENSOR_MAP_INTERLEAVE_NONE, swz, CU_TENSOR_MAP_L2_PROMOTION_L2_128B, CU_TENSOR_MAP_FLOAT_OOB_FILL_NONE);
}

}

extern "C" void kernel_launch(void* const* d_in, const int* in_sizes, int n_in, void* d_out, int out_size) {
  (void)in_sizes; (void)n_in; (void)out_size;
  Params p;
  p.q = (const __nv_bfloat16*)d_in[0];
  p.k = (const __nv_bfloat16*)d_in[1];
  p.v = (const __nv_bfloat16*)d_in[2];
  p.shift_k = (const __nv_bfloat16*)d_in[3];
  p.ssm_k = (const __nv_bfloat16*)d_in[4];
  p.ssm_D = (const __nv_bfloat16*)d_in[5];
  p.wqkv = (const __nv_bfloat16*)d_in[7];
  p.wo = (const __nv_bfloat16*)d_in[8];
  p.gate_w = (const __nv_bfloat16*)d_in[9];
  p.out = (__nv_bfloat16*)d_out;
  p.zero = 0;

  static EncodeFn fn = nullptr;
  static void *yaddr = nullptr, *oaddr = nullptr;
  if (!fn) {
    cudaDriverEntryPointQueryResult qr;
    void* f = nullptr;
    cudaGetDriverEntryPoint("cuTensorMapEncodeTiled", &f, cudaEnableDefault, &qr);
    fn = (EncodeFn)f;
    cudaGetSymbolAddress(&yaddr, g_U);
    cudaGetSymbolAddress(&oaddr, g_O);
    cudaFuncSetAttribute(fused_kernel, cudaFuncAttributeMaxDynamicSharedMemorySize, SMEM_BYTES);
  }
  Maps m;
  {
    const cuuint64_t dims[3] = {640, 1024, 2}, st[2] = {2560, 1280};
    const cuuint32_t box[3] = {64, 64, 2};
    encode(fn, &m.x, p.q, 3, dims, st, box, CU_TENSOR_MAP_SWIZZLE_128B);
  }
  {
    const cuuint64_t dims[3] = {640, 640, 3}, st[2] = {3840, 1280};
    const cuuint32_t box[3] = {64, 64, 3}, boxt[3] = {16, 64, 3};
    encode(fn, &m.wm, p.wqkv, 3, dims, st, box, CU_TENSOR_MAP_SWIZZLE_128B);
    encode(fn, &m.wt, p.wqkv, 3, dims, st, boxt, CU_TENSOR_MAP_SWIZZLE_32B);
    const cuuint32_t boxh[3] = {64, 16, 3};
    encode(fn, &m.wh, p.wqkv, 3, dims, st, boxh, CU_TENSOR_MAP_SWIZZLE_128B);
  }
  {
    const cuuint64_t dims[3] = {64, 2048, 10}, st[2] = {1280, 128};
    const cuuint32_t boxk[3] = {64, 35, 1}, boxv[3] = {64, 32, 1};
    encode(fn, &m.k, p.k, 3, dims, st, boxk, CU_TENSOR_MAP_SWIZZLE_128B);
    encode(fn, &m.v, p.v, 3, dims, st, boxv, CU_TENSOR_MAP_SWIZZLE_128B);
  }
  {
    const cuuint64_t dims[3] = {16, 640, 40}, st[2] = {1280, 32};
    const cuuint32_t box[3] = {16, 40, 5};
    encode(fn, &m.wo, p.wo, 3, dims, st, box, CU_TENSOR_MAP_SWIZZLE_32B);
  }
  {
    const cuuint64_t dims[2] = {2048, 640}, st[1] = {U_PITCH * 16};
    const cuuint32_t box[2] = {64, 80};
    encode(fn, &m.y, yaddr, 2, dims, st, box, CU_TENSOR_MAP_SWIZZLE_128B);
    const cuuint64_t dl[2] = {64, DIM * U_PITCH / 8}, dol[2] = {64, NCTA * 160}, sl[1] = {128};
    const cuuint32_t bl[2] = {16, 32}, bol[2] = {16, 160};
    encode(fn, &m.yl, yaddr, 2, dl, sl, bl, CU_TENSOR_MAP_SWIZZLE_NONE);
    encode(fn, &m.ol, oaddr, 2, dol, sl, bol, CU_TENSOR_MAP_SWIZZLE_NONE);
  }
  {
    const cuuint64_t dims[2] = {640, 2048}, st[1] = {1280};
    const cuuint32_t bqm[2] = {64, 128}, bqt[2] = {16, 128}, bom[2] = {64, 16}, bot[2] = {16, 16};
    encode(fn, &m.qm, p.q, 2, dims, st, bqm, CU_TENSOR_MAP_SWIZZLE_128B);
    encode(fn, &m.qt, p.q, 2, dims, st, bqt, CU_TENSOR_MAP_SWIZZLE_32B);
    encode(fn, &m.om, p.out, 2, dims, st, bom, CU_TENSOR_MAP_SWIZZLE_128B);
    encode(fn, &m.ot, p.out, 2, dims, st, bot, CU_TENSOR_MAP_SWIZZLE_32B);
  }
  fused_kernel<<<NCTA, NTHR, SMEM_BYTES>>>(m, p);
}
```

```cpp
#include <cuda.h>
#include <cuda_bf16.h>
#include <cuda_runtime.h>
#include <stdint.h>

namespace {

constexpr int SEQ = 2048, DIM = 640, NCTA = 128, NTHR = 512;

#define KV_KB 2
#define DEV_EXIT 0
#define FENCE_LO 0
#define FENCE_HI 0
#define WB_TRIG B_USIG
#define T_ISSUE 288
#define FC_AT 1
#define T_INIT 448
#define TASK0 0x3
#define TASK1 0x52
#define TASK2 0x41

constexpr uint32_t STAGE_BYTES = 47104, ST_W = 16384, ST_WT = 40960;
constexpr uint32_t O_BYTES = 20480, WO_BYTES = 12800;
constexpr uint32_t OFF_OA = 0;
constexpr uint32_t OFF_QS = 3 * O_BYTES, OFF_QT = OFF_QS + 16384;
constexpr uint32_t OFF_WC = 81920;
constexpr uint32_t OFF_WA = 94720;
constexpr uint32_t OFF_GATE = 145920;
constexpr uint32_t OFF_TT = 146432;
constexpr uint32_t OFF_KVX = 148480;
constexpr uint32_t OFF_CH3 = 163840;
constexpr uint32_t CH_BYTES = 12288, U_BYTES = 4096;
constexpr uint32_t OFF_FT = 225280, OFF_GT = 229376;
constexpr uint32_t OFF_CH0 = 188416;
constexpr uint32_t OFF_KVS = OFF_CH0, KVS_V = 4480, KVS_BYTES = 8576;
constexpr uint32_t OFF_YT = 163840;
constexpr uint32_t OFF_BAR = 231936;
constexpr uint32_t SMEM_BYTES = OFF_BAR + 512;

enum : uint32_t {
  B_EMPTY1 = 0, B_S3 = 3, B_E3 = 4, B_EMPTY2 = 5, B_ATTN = 9, B_P1 = 10,
  B_GATE = 11, B_HA = 12, B_KVD = 13, B_PREP = 14, B_YST = 15,
  B_CVD = 20,
  B_FULL2 = 21, B_U = 29, B_KV = 33, B_HB = 38, B_C34 = 39, B_YRB = 40, B_YFULL = 41, B_EPOCH = 42, B_LAST = 43,
  B_WOP = 44, B_USIG = 45, B_WST = 46, B_QF = 47, B_ORB = 48,
  B_F0 = 49, B_FULL1 = 53
};
constexpr uint32_t OFF_EPOCH = OFF_BAR + 8 * 58, OFF_D = OFF_BAR + 8 * 60;
__device__ __forceinline__ uint32_t off_o(int j) { return j < 4 ? OFF_OA + j * O_BYTES : j < 6 ? OFF_CH0 + (j - 4) * O_BYTES : OFF_OA + (j - 6) * O_BYTES; }
__device__ __forceinline__ uint32_t off_w(int j) { return j < 4 ? OFF_WA + j * WO_BYTES : j == 4 ? OFF_KVX : j == 5 ? OFF_WC : OFF_WA + (j - 6) * WO_BYTES; }
__device__ __forceinline__ int step_src(int hg, int j) { return j == 0 ? hg : j <= hg ? j - 1 : j; }
__device__ __forceinline__ bool tail_first(int hg) { return (hg & 3) == 3; }
__device__ __forceinline__ uint32_t off_ch(int c) { return (c < 3 ? OFF_CH0 : OFF_CH3 - 3 * CH_BYTES) + c * CH_BYTES; }

#define U_PITCH 264
__device__ __align__(1024) uint4 g_U[DIM * U_PITCH];
__device__ __align__(128) uint4 g_O[NCTA * 1280];
__device__ uint4 g_WO[64 * 800];
__device__ uint4 g_halo[NCTA * 2 * 7 * 32];
__device__ __align__(128) float g_gate[SEQ];
__device__ unsigned g_cnt[32 * (1 + 2 * 16 + 8 + NCTA)];
constexpr int C_LAUNCH = 0, C_PREP = 32, C_Y = 32 * 17, C_W = 32 * 33, C_O = 32 * 41;

#define TSM(cond, slot) do { } while (0)
#define TSIF(cond, slot) do { if (__LINE__ >= FENCE_LO && __LINE__ < FENCE_HI) sched_fence(); } while (0)
__device__ __forceinline__ void sched_fence() {
  asm volatile("{\n.reg .pred p;\n.reg .u32 c;\nmov.u32 c, %%clock;\nsetp.eq.u32 p, c, 0;\n@p st.shared.u32 [%0], c;\n}"
               ::"r"(1024 + OFF_EPOCH + 4) : "memory");
}
#define TS(slot) TSIF(true, slot)

struct Params {
  const __nv_bfloat16 *q, *k, *v, *shift_k, *ssm_k, *ssm_D, *wqkv, *wo, *gate_w;
  __nv_bfloat16* out;
  uint32_t zero;
};

constexpr int SPIN_LIMIT = 1 << 17;

__device__ __forceinline__ void mbar_init(uint32_t bar, uint32_t count) {
  asm volatile("mbarrier.init.shared::cta.b64 [%0], %1;" ::"r"(bar), "r"(count) : "memory");
}
__device__ __forceinline__ void mbar_expect_tx(uint32_t bar, uint32_t bytes) {
  asm volatile("mbarrier.arrive.expect_tx.shared::cta.b64 _, [%0], %1;" ::"r"(bar), "r"(bytes) : "memory");
}
__device__ __forceinline__ void mbar_arrive(uint32_t bar) {
  asm volatile("mbarrier.arrive.shared::cta.b64 _, [%0];" ::"r"(bar) : "memory");
}
__device__ __forceinline__ void mbar_wait(uint32_t bar, uint32_t parity) {
  uint32_t ok;
  int spins = 0;
  do {
      asm volatile("{\n.reg .pred p;\nmbarrier.try_wait.parity.shared::cta.b64 p, [%1], %2;\nselp.b32 %0, 1, 0, p;\n}"
                   : "=r"(ok) : "r"(bar), "r"(parity) : "memory");
    if (++spins > SPIN_LIMIT) break;
  } while (!ok);
}
__device__ __forceinline__ unsigned flag_read(const unsigned* p) {
  unsigned v;
  asm volatile("ld.relaxed.gpu.global.u32 %0, [%1];" : "=r"(v) : "l"(p) : "memory");
  return v;
}
__device__ __forceinline__ void flag_poll(const unsigned* p, unsigned target) {
  unsigned v;
  int spins = 0;
  do {
    asm volatile("ld.relaxed.gpu.global.u32 %0, [%1];" : "=r"(v) : "l"(p) : "memory");
    if (++spins > SPIN_LIMIT) break;
  } while ((int)(v - target) < 0);
}
__device__ __forceinline__ void flag_wait(const unsigned* p, unsigned target) {
  flag_poll(p, target);
}
__device__ __forceinline__ void flag_signal(unsigned* p, int n, int lane) {
  if (lane == 0) asm volatile("fence.release.gpu;" ::: "memory");
  __syncwarp();
  if (lane < n) asm volatile("red.relaxed.gpu.global.add.u32 [%0], 1;" ::"l"(p + 32 * lane) : "memory");
}
__device__ __forceinline__ void flag_bump(unsigned* p) {
  asm volatile("red.relaxed.gpu.global.add.u32 [%0], 1;" ::"l"(p) : "memory");
}
__device__ __forceinline__ void fence_async_smem() { asm volatile("fence.proxy.async.shared::cta;" ::: "memory"); }
__device__ __forceinline__ void wg_sync(int id) { asm volatile("bar.sync %0, 128;" ::"r"(id) : "memory"); }

__device__ __forceinline__ void tma_2d(uint32_t dst, const CUtensorMap* tm, int c0, int c1, uint32_t bar) {
  asm volatile("cp.async.bulk.tensor.2d.shared::cluster.global.mbarrier::complete_tx::bytes [%0], [%1, {%3, %4}], [%2];"
               ::"r"(dst), "l"(tm), "r"(bar), "r"(c0), "r"(c1) : "memory");
}
__device__ __forceinline__ void tma_3d(uint32_t dst, const CUtensorMap* tm, int c0, int c1, int c2, uint32_t bar) {
  asm volatile("cp.async.bulk.tensor.3d.shared::cluster.global.mbarrier::complete_tx::bytes [%0], [%1, {%3, %4, %5}], [%2];"
               ::"r"(dst), "l"(tm), "r"(bar), "r"(c0), "r"(c1), "r"(c2) : "memory");
}
__device__ __forceinline__ void bulk_load(uint32_t dst, const void* src, uint32_t bytes, uint32_t bar) {
  asm volatile("cp.async.bulk.shared::cluster.global.mbarrier::complete_tx::bytes [%0], [%1], %2, [%3];"
               ::"r"(dst), "l"(src), "r"(bytes), "r"(bar) : "memory");
}
__device__ __forceinline__ void bulk_store(void* dst, uint32_t src, uint32_t bytes) {
  asm volatile("cp.async.bulk.global.shared::cta.bulk_group [%0], [%1], %2;" ::"l"(dst), "r"(src), "r"(bytes) : "memory");
}
__device__ __forceinline__ void bulk_wait_read() {
  asm volatile("cp.async.bulk.commit_group;\ncp.async.bulk.wait_group.read 0;" ::: "memory");
}

__device__ __forceinline__ void publish(void* dst, uint32_t src, uint32_t bytes) {
  bulk_store(dst, src, bytes);
  bulk_wait_read();
}

__device__ __forceinline__ void wg_fence() { asm volatile("wgmma.fence.sync.aligned;" ::: "memory"); }
__device__ __forceinline__ void wg_commit() { asm volatile("wgmma.commit_group.sync.aligned;" ::: "memory"); }
template <int N> __device__ __forceinline__ void wg_wait() { asm volatile("wgmma.wait_group.sync.aligned %0;" ::"n"(N) : "memory"); }
__device__ __forceinline__ uint32_t desc_lo(uint32_t addr, uint32_t lbo) { return ((addr & 0x3FFFF) >> 4) | ((lbo >> 4) << 16); }
constexpr uint32_t desc_hi(uint32_t sbo, uint32_t swz) { return (sbo >> 4) | (swz << 30); }
constexpr uint32_t HI_SW128 = desc_hi(1024, 1), HI_SW64 = desc_hi(512, 2), HI_SW32 = desc_hi(256, 3), HI_NONE = desc_hi(128, 0);
template <int N> __device__ __forceinline__ void pin(float* d) {
#pragma unroll
  for (int i = 0; i < N; i++) asm volatile("" : "+f"(d[i])::"memory");
}

__device__ __forceinline__ uint32_t lds32(uint32_t a) {
  uint32_t v;
  asm volatile("ld.volatile.shared.u32 %0, [%1];" : "=r"(v) : "r"(a) : "memory");
  return v;
}
__device__ __forceinline__ uint2 ldg64(const void* a) {
  uint2 v;
  asm volatile("ld.global.nc.v2.u32 {%0, %1}, [%2];" : "=r"(v.x), "=r"(v.y) : "l"(a) : "memory");
  return v;
}
__device__ __forceinline__ void ldsm4(uint32_t* r, uint32_t a) {
  asm volatile("ldmatrix.sync.aligned.m8n8.x4.shared.b16 {%0, %1, %2, %3}, [%4];"
               : "=r"(r[0]), "=r"(r[1]), "=r"(r[2]), "=r"(r[3]) : "r"(a) : "memory");
}
__device__ __forceinline__ void ldsm4t(uint32_t* r, uint32_t a) {
  asm volatile("ldmatrix.sync.aligned.m8n8.x4.trans.shared.b16 {%0, %1, %2, %3}, [%4];"
               : "=r"(r[0]), "=r"(r[1]), "=r"(r[2]), "=r"(r[3]) : "r"(a) : "memory");
}
__device__ __forceinline__ uint2 lds64(uint32_t a) {
  uint2 v;
  asm volatile("ld.shared.v2.u32 {%0, %1}, [%2];" : "=r"(v.x), "=r"(v.y) : "r"(a) : "memory");
  return v;
}
__device__ __forceinline__ uint4 lds128(uint32_t a) {
  uint4 v;
  asm volatile("ld.shared.v4.u32 {%0, %1, %2, %3}, [%4];" : "=r"(v.x), "=r"(v.y), "=r"(v.z), "=r"(v.w) : "r"(a) : "memory");
  return v;
}
__device__ __forceinline__ void sts128(uint32_t a, uint32_t x, uint32_t y, uint32_t z, uint32_t w) {
  asm volatile("st.shared.v4.u32 [%0], {%1, %2, %3, %4};" ::"r"(a), "r"(x), "r"(y), "r"(z), "r"(w) : "memory");
}
__device__ __forceinline__ void stsm4(uint32_t a, const uint32_t* r) {
  asm volatile("stmatrix.sync.aligned.m8n8.x4.shared.b16 [%0], {%1, %2, %3, %4};" ::"r"(a), "r"(r[0]), "r"(r[1]), "r"(r[2]), "r"(r[3]) : "memory");
}
__device__ __forceinline__ uint32_t pack2(float lo, float hi) {
  uint32_t r;
  asm("cvt.rn.bf16x2.f32 %0, %1, %2;" : "=r"(r) : "f"(hi), "f"(lo));
  return r;
}
__device__ __forceinline__ uint32_t movm(uint32_t a) {
  uint32_t d;
  asm volatile("movmatrix.sync.aligned.m8n8.trans.b16 %0, %1;" : "=r"(d) : "r"(a));
  return d;
}
__device__ __forceinline__ uint32_t bmul(uint32_t a, uint32_t b) {
  uint32_t d;
  asm("mul.rn.bf16x2 %0, %1, %2;" : "=r"(d) : "r"(a), "r"(b));
  return d;
}
__device__ __forceinline__ uint32_t badd(uint32_t a, uint32_t b) {
  uint32_t d;
  asm("add.rn.bf16x2 %0, %1, %2;" : "=r"(d) : "r"(a), "r"(b));
  return d;
}
__device__ __forceinline__ uint32_t bfma(uint32_t a, uint32_t b, uint32_t c) {
  uint32_t d;
  asm("fma.rn.bf16x2 %0, %1, %2, %3;" : "=r"(d) : "r"(a), "r"(b), "r"(c));
  return d;
}
__device__ __forceinline__ float bf_lo(uint32_t x) { return __uint_as_float(x << 16); }
__device__ __forceinline__ float bf_hi(uint32_t x) { return __uint_as_float(x & 0xFFFF0000u); }
__device__ __forceinline__ float ex2(float x) {
  float y;
  asm("ex2.approx.ftz.f32 %0, %1;" : "=f"(y) : "f"(x));
  return y;
}
__device__ __forceinline__ float rcp(float x) {
  float y;
  asm("rcp.approx.ftz.f32 %0, %1;" : "=f"(y) : "f"(x));
  return y;
}
__device__ __forceinline__ void mma16816(float* d, uint32_t a0, uint32_t a1, uint32_t a2, uint32_t a3, uint32_t b0, uint32_t b1) {
  asm volatile("mma.sync.aligned.m16n8k16.row.col.f32.bf16.bf16.f32 {%0, %1, %2, %3}, {%4, %5, %6, %7}, {%8, %9}, {%0, %1, %2, %3};"
               : "+f"(d[0]), "+f"(d[1]), "+f"(d[2]), "+f"(d[3])
               : "r"(a0), "r"(a1), "r"(a2), "r"(a3), "r"(b0), "r"(b1));
}
__device__ __forceinline__ void mma1688(float* d, uint32_t a0, uint32_t a1, uint32_t b0) {
  asm volatile("mma.sync.aligned.m16n8k8.row.col.f32.bf16.bf16.f32 {%0, %1, %2, %3}, {%4, %5}, {%6}, {%0, %1, %2, %3};"
               : "+f"(d[0]), "+f"(d[1]), "+f"(d[2]), "+f"(d[3])
               : "r"(a0), "r"(a1), "r"(b0));
}

template <int N> struct WgRS;
template <int N> struct WgSST;
template <> struct WgRS<32> {
  template <uint32_t HB>
  static __device__ __forceinline__ void mma(float* d, const uint32_t* a, uint32_t db) {
    asm volatile("{\n.reg .pred p;\n.reg .b64 db;\nsetp.ne.b32 p, %22, 0;\n"
      "mov.b64 db, {%20, %21};\n"
      "wgmma.mma_async.sync.aligned.m64n32k16.f32.bf16.bf16 {"
      "%0, %1, %2, %3, %4, %5, %6, %7, %8, %9, %10, %11, %12, %13, %14, %15"
      "}, {%16, %17, %18, %19}, db, p, 1, 1, 1;\n}\n"
      : "+f"(d[0]), "+f"(d[1]), "+f"(d[2]), "+f"(d[3]), "+f"(d[4]), "+f"(d[5]), "+f"(d[6]), "+f"(d[7]),
        "+f"(d[8]), "+f"(d[9]), "+f"(d[10]), "+f"(d[11]), "+f"(d[12]), "+f"(d[13]), "+f"(d[14]), "+f"(d[15])
      : "r"(a[0]), "r"(a[1]), "r"(a[2]), "r"(a[3]), "r"(db), "n"(HB), "n"(1));
  }
  template <uint32_t HB>
  static __device__ __forceinline__ void set(float* d, const uint32_t* a, uint32_t db) {
    asm volatile("{\n.reg .pred p;\n.reg .b64 db;\nsetp.ne.b32 p, %22, 0;\n"
      "mov.b64 db, {%20, %21};\n"
      "wgmma.mma_async.sync.aligned.m64n32k16.f32.bf16.bf16 {"
      "%0, %1, %2, %3, %4, %5, %6, %7, %8, %9, %10, %11, %12, %13, %14, %15"
      "}, {%16, %17, %18, %19}, db, p, 1, 1, 1;\n}\n"
      : "=f"(d[0]), "=f"(d[1]), "=f"(d[2]), "=f"(d[3]), "=f"(d[4]), "=f"(d[5]), "=f"(d[6]), "=f"(d[7]),
        "=f"(d[8]), "=f"(d[9]), "=f"(d[10]), "=f"(d[11]), "=f"(d[12]), "=f"(d[13]), "=f"(d[14]), "=f"(d[15])
      : "r"(a[0]), "r"(a[1]), "r"(a[2]), "r"(a[3]), "r"(db), "n"(HB), "n"(0));
  }
};
template <> struct WgRS<64> {
  template <uint32_t HB>
  static __device__ __forceinline__ void mma(float* d, const uint32_t* a, uint32_t db) {
    asm volatile("{\n.reg .pred p;\n.reg .b64 db;\nsetp.ne.b32 p, %38, 0;\n"
      "mov.b64 db, {%36, %37};\n"
      "wgmma.mma_async.sync.aligned.m64n64k16.f32.bf16.bf16 {"
      "%0, %1, %2, %3, %4, %5, %6, %7, %8, %9, %10, %11, %12, %13, %14, %15, "
      "%16, %17, %18, %19, %20, %21, %22, %23, %24, %25, %26, %27, %28, %29, %30, %31"
      "}, {%32, %33, %34, %35}, db, p, 1, 1, 1;\n}\n"
      : "+f"(d[0]), "+f"(d[1]), "+f"(d[2]), "+f"(d[3]), "+f"(d[4]), "+f"(d[5]), "+f"(d[6]), "+f"(d[7]),
        "+f"(d[8]), "+f"(d[9]), "+f"(d[10]), "+f"(d[11]), "+f"(d[12]), "+f"(d[13]), "+f"(d[14]), "+f"(d[15]),
        "+f"(d[16]), "+f"(d[17]), "+f"(d[18]), "+f"(d[19]), "+f"(d[20]), "+f"(d[21]), "+f"(d[22]), "+f"(d[23]),
        "+f"(d[24]), "+f"(d[25]), "+f"(d[26]), "+f"(d[27]), "+f"(d[28]), "+f"(d[29]), "+f"(d[30]), "+f"(d[31])
      : "r"(a[0]), "r"(a[1]), "r"(a[2]), "r"(a[3]), "r"(db), "n"(HB), "n"(1));
  }
  template <uint32_t HB>
  static __device__ __forceinline__ void set(float* d, const uint32_t* a, uint32_t db) {
    asm volatile("{\n.reg .pred p;\n.reg .b64 db;\nsetp.ne.b32 p, %38, 0;\n"
      "mov.b64 db, {%36, %37};\n"
      "wgmma.mma_async.sync.aligned.m64n64k16.f32.bf16.bf16 {"
      "%0, %1, %2, %3, %4, %5, %6, %7, %8, %9, %10, %11, %12, %13, %14, %15, "
      "%16, %17, %18, %19, %20, %21, %22, %23, %24, %25, %26, %27, %28, %29, %30, %31"
      "}, {%32, %33, %34, %35}, db, p, 1, 1, 1;\n}\n"
      : "=f"(d[0]), "=f"(d[1]), "=f"(d[2]), "=f"(d[3]), "=f"(d[4]), "=f"(d[5]), "=f"(d[6]), "=f"(d[7]),
        "=f"(d[8]), "=f"(d[9]), "=f"(d[10]), "=f"(d[11]), "=f"(d[12]), "=f"(d[13]), "=f"(d[14]), "=f"(d[15]),
        "=f"(d[16]), "=f"(d[17]), "=f"(d[18]), "=f"(d[19]), "=f"(d[20]), "=f"(d[21]), "=f"(d[22]), "=f"(d[23]),
        "=f"(d[24]), "=f"(d[25]), "=f"(d[26]), "=f"(d[27]), "=f"(d[28]), "=f"(d[29]), "=f"(d[30]), "=f"(d[31])
      : "r"(a[0]), "r"(a[1]), "r"(a[2]), "r"(a[3]), "r"(db), "n"(HB), "n"(0));
  }
};
template <> struct WgSST<48> {
  template <uint32_t HA, uint32_t HB>
  static __device__ __forceinline__ void mma(float* d, uint32_t da, uint32_t db, int sc) {
    asm volatile("{\n.reg .pred p;\n.reg .b64 da, db;\nsetp.ne.b32 p, %28, 0;\n"
      "mov.b64 da, {%24, %25};\nmov.b64 db, {%26, %27};\n"
      "wgmma.mma_async.sync.aligned.m64n48k16.f32.bf16.bf16 {"
      "%0, %1, %2, %3, %4, %5, %6, %7, %8, %9, %10, %11, %12, %13, %14, %15, "
      "%16, %17, %18, %19, %20, %21, %22, %23"
      "}, da, db, p, 1, 1, 0, 1;\n}\n"
      : "+f"(d[0]), "+f"(d[1]), "+f"(d[2]), "+f"(d[3]), "+f"(d[4]), "+f"(d[5]), "+f"(d[6]), "+f"(d[7]),
        "+f"(d[8]), "+f"(d[9]), "+f"(d[10]), "+f"(d[11]), "+f"(d[12]), "+f"(d[13]), "+f"(d[14]), "+f"(d[15]),
        "+f"(d[16]), "+f"(d[17]), "+f"(d[18]), "+f"(d[19]), "+f"(d[20]), "+f"(d[21]), "+f"(d[22]), "+f"(d[23])
      : "r"(da), "n"(HA), "r"(db), "n"(HB), "r"(sc));
  }
};
template <> struct WgSST<80> {
  template <uint32_t HA, uint32_t HB>
  static __device__ __forceinline__ void mma(float* d, uint32_t da, uint32_t db, int sc) {
    asm volatile("{\n.reg .pred p;\n.reg .b64 da, db;\nsetp.ne.b32 p, %44, 0;\n"
      "mov.b64 da, {%40, %41};\nmov.b64 db, {%42, %43};\n"
      "wgmma.mma_async.sync.aligned.m64n80k16.f32.bf16.bf16 {"
      "%0, %1, %2, %3, %4, %5, %6, %7, %8, %9, %10, %11, %12, %13, %14, %15, "
      "%16, %17, %18, %19, %20, %21, %22, %23, %24, %25, %26, %27, %28, %29, %30, %31, "
      "%32, %33, %34, %35, %36, %37, %38, %39"
      "}, da, db, p, 1, 1, 0, 1;\n}\n"
      : "+f"(d[0]), "+f"(d[1]), "+f"(d[2]), "+f"(d[3]), "+f"(d[4]), "+f"(d[5]), "+f"(d[6]), "+f"(d[7]),
        "+f"(d[8]), "+f"(d[9]), "+f"(d[10]), "+f"(d[11]), "+f"(d[12]), "+f"(d[13]), "+f"(d[14]), "+f"(d[15]),
        "+f"(d[16]), "+f"(d[17]), "+f"(d[18]), "+f"(d[19]), "+f"(d[20]), "+f"(d[21]), "+f"(d[22]), "+f"(d[23]),
        "+f"(d[24]), "+f"(d[25]), "+f"(d[26]), "+f"(d[27]), "+f"(d[28]), "+f"(d[29]), "+f"(d[30]), "+f"(d[31]),
        "+f"(d[32]), "+f"(d[33]), "+f"(d[34]), "+f"(d[35]), "+f"(d[36]), "+f"(d[37]), "+f"(d[38]), "+f"(d[39])
      : "r"(da), "n"(HA), "r"(db), "n"(HB), "r"(sc));
  }
};
template <> struct WgSST<192> {
  template <uint32_t HA, uint32_t HB>
  static __device__ __forceinline__ void mma(float* d, uint32_t da, uint32_t db, int sc) {
    asm volatile("{\n.reg .pred p;\n.reg .b64 da, db;\nsetp.ne.b32 p, %100, 0;\n"
      "mov.b64 da, {%96, %97};\nmov.b64 db, {%98, %99};\n"
      "wgmma.mma_async.sync.aligned.m64n192k16.f32.bf16.bf16 {"
      "%0, %1, %2, %3, %4, %5, %6, %7, %8, %9, %10, %11, %12, %13, %14, %15, "
      "%16, %17, %18, %19, %20, %21, %22, %23, %24, %25, %26, %27, %28, %29, %30, %31, "
      "%32, %33, %34, %35, %36, %37, %38, %39, %40, %41, %42, %43, %44, %45, %46, %47, "
      "%48, %49, %50, %51, %52, %53, %54, %55, %56, %57, %58, %59, %60, %61, %62, %63, "
      "%64, %65, %66, %67, %68, %69, %70, %71, %72, %73, %74, %75, %76, %77, %78, %79, "
      "%80, %81, %82, %83, %84, %85, %86, %87, %88, %89, %90, %91, %92, %93, %94, %95"
      "}, da, db, p, 1, 1, 0, 1;\n}\n"
      : "+f"(d[0]), "+f"(d[1]), "+f"(d[2]), "+f"(d[3]), "+f"(d[4]), "+f"(d[5]), "+f"(d[6]), "+f"(d[7]),
        "+f"(d[8]), "+f"(d[9]), "+f"(d[10]), "+f"(d[11]), "+f"(d[12]), "+f"(d[13]), "+f"(d[14]), "+f"(d[15]),
        "+f"(d[16]), "+f"(d[17]), "+f"(d[18]), "+f"(d[19]), "+f"(d[20]), "+f"(d[21]), "+f"(d[22]), "+f"(d[23]),
        "+f"(d[24]), "+f"(d[25]), "+f"(d[26]), "+f"(d[27]), "+f"(d[28]), "+f"(d[29]), "+f"(d[30]), "+f"(d[31]),
        "+f"(d[32]), "+f"(d[33]), "+f"(d[34]), "+f"(d[35]), "+f"(d[36]), "+f"(d[37]), "+f"(d[38]), "+f"(d[39]),
        "+f"(d[40]), "+f"(d[41]), "+f"(d[42]), "+f"(d[43]), "+f"(d[44]), "+f"(d[45]), "+f"(d[46]), "+f"(d[47]),
        "+f"(d[48]), "+f"(d[49]), "+f"(d[50]), "+f"(d[51]), "+f"(d[52]), "+f"(d[53]), "+f"(d[54]), "+f"(d[55]),
        "+f"(d[56]), "+f"(d[57]), "+f"(d[58]), "+f"(d[59]), "+f"(d[60]), "+f"(d[61]), "+f"(d[62]), "+f"(d[63]),
        "+f"(d[64]), "+f"(d[65]), "+f"(d[66]), "+f"(d[67]), "+f"(d[68]), "+f"(d[69]), "+f"(d[70]), "+f"(d[71]),
        "+f"(d[72]), "+f"(d[73]), "+f"(d[74]), "+f"(d[75]), "+f"(d[76]), "+f"(d[77]), "+f"(d[78]), "+f"(d[79]),
        "+f"(d[80]), "+f"(d[81]), "+f"(d[82]), "+f"(d[83]), "+f"(d[84]), "+f"(d[85]), "+f"(d[86]), "+f"(d[87]),
        "+f"(d[88]), "+f"(d[89]), "+f"(d[90]), "+f"(d[91]), "+f"(d[92]), "+f"(d[93]), "+f"(d[94]), "+f"(d[95])
      : "r"(da), "n"(HA), "r"(db), "n"(HB), "r"(sc));
  }
};

struct FftConst {
  uint32_t f[2][4], fi[4][4];
  uint32_t ta[2][2], tb[2][2];
};
__device__ __forceinline__ void cis(int m, float scale, float& c, float& s) {
  const float a = (float)m * (-6.283185307179586f * scale);
  c = __cosf(a);
  s = __sinf(a);
}
__device__ __forceinline__ void fft_tables(uint32_t (&v)[12], int tw) {
  const int row = tw >> 2, ch = tw & 3;
#pragma unroll
  for (int i = 0; i < 4; i++) {
    float c[2], s[2], x[2];
#pragma unroll
    for (int e = 0; e < 2; e++) {
      cis((((32 * (8 * ch + 2 * i + e) + 15) * (4 * row - 63) + 2048) & 4095) - 2048, 1.f / 4096, c[e], s[e]);
      float gc, gs;
      cis((((row & 15) * (8 * (ch & 1) + 2 * i + e) + 8) & 15) - 8, 1.f / 16, gc, gs);
      x[e] = (row >> 4) == (ch >> 1) ? gc : (ch >> 1) ? gs : -gs;
    }
    v[i] = pack2(c[0] * 0.125f, c[1] * 0.125f);
    v[4 + i] = pack2(s[0] * 0.125f, s[1] * 0.125f);
    v[8 + i] = pack2(x[0], x[1]);
  }
#pragma unroll
  for (int i = 0; i < 12; i++) asm volatile("" : "+r"(v[i]));
}
__device__ __forceinline__ void fft_tables_store(const uint32_t (&v)[12], uint32_t sb, int tw) {
  const int row = tw >> 2;
  const uint32_t x = ((tw ^ (row >> 1)) & 3) << 4, a = sb + OFF_FT + (16 * (row >> 3) + (row & 7)) * 64 + x;
  sts128(a, v[0], v[1], v[2], v[3]);
  sts128(a + 512, v[4], v[5], v[6], v[7]);
  sts128(sb + OFF_GT + row * 64 + x, v[8], v[9], v[10], v[11]);
}
__device__ __forceinline__ void fft_twiddles(uint32_t (&v)[2], int tw) {
  float a[2], s[2];
#pragma unroll
  for (int i = 0; i < 2; i++) {
    float c;
    cis((2 * (2 * (tw & 3) + i) - 15) * (4 * (tw >> 2) - 63), 1.f / 4096, c, s[i]);
    a[i] = __fdividef(-s[i], 1.f + c);
  }
  v[0] = pack2(a[0], a[1]);
  v[1] = pack2(s[0], s[1]);
  asm volatile("" : "+r"(v[0]), "+r"(v[1]));
}
__device__ __forceinline__ void fft_matrices(FftConst& k, uint32_t sb, int w, int lane) {
  const uint32_t x = (lane >> 1) & 3;
  const uint2 t0 = lds64(sb + OFF_TT + 256 * w + 8 * lane), t1 = lds64(sb + OFF_TT + 256 * w + 8 * (lane ^ 3));
  k.ta[0][0] = t0.x;
  k.tb[0][0] = t0.y;
  k.ta[1][1] = __byte_perm(t1.x, 0, 0x1032);
  k.tb[1][1] = __byte_perm(t1.y, 0, 0x1032);
#pragma unroll
  for (int j = 0; j < 2; j++) {
    k.ta[1 - j][j] = k.ta[j][j] ^ 0x80008000u;
    k.tb[1 - j][j] = k.tb[j][j] ^ 0x80008000u;
    asm volatile("" : "+r"(k.ta[0][j]), "+r"(k.tb[0][j]), "+r"(k.ta[1][j]), "+r"(k.tb[1][j]));
  }
#pragma unroll
  for (int i = 0; i < 2; i++) {
    ldsm4(k.f[i], sb + OFF_FT + (16 * w + (lane & 15)) * 64 + (((2 * i + (lane >> 4)) ^ x) << 4));
    ldsm4t(k.fi[i], sb + OFF_FT + (32 * i + lane) * 64 + ((w ^ x) << 4));
#pragma unroll
    for (int j = 0; j < 4; j++) {
      k.fi[2 + i][j] = (j & 1) ? k.fi[i][j - 1] ^ 0x80008000u : k.fi[i][j + 1];
      asm volatile("" : "+r"(k.fi[2 + i][j]));
    }
  }
}
__device__ __forceinline__ void rot(uint32_t& x, uint32_t& y, uint32_t a, uint32_t b) {
  x = bfma(a, y, x);
  y = bfma(b, x, y);
  x = bfma(a, y, x);
}
__device__ __forceinline__ void twiddle_fwd(uint32_t (&a)[4][4], float* d, const FftConst& k) {
#pragma unroll
  for (int q = 0; q < 4; q++)
#pragma unroll
    for (int j = 0; j < 2; j++) {
      const float* x = d + 8 * q + 4 * j;
      uint32_t re = pack2(x[0], x[1]), im = pack2(x[2], x[3]);
      rot(re, im, k.ta[0][j], k.tb[0][j]);
      a[q & 2][2 * j + (q & 1)] = re;
      a[(q & 2) + 1][2 * j + (q & 1)] = im;
    }
}
__device__ __forceinline__ void g_step(float* d, const uint32_t (&a)[4][4], uint32_t dre, uint32_t dim) {
  WgRS<32>::set<HI_SW64>(d, a[0], dre);
  WgRS<32>::set<HI_SW64>(d + 16, a[2], dre);
  WgRS<32>::mma<HI_SW64>(d, a[1], dim);
  WgRS<32>::mma<HI_SW64>(d + 16, a[3], dim);
  wg_commit();
}

__device__ __forceinline__ void products(uint32_t (&a)[4][4], const float* H, const float* U, int p) {
#pragma unroll
  for (int j = 0; j < 2; j++)
#pragma unroll
    for (int m = 2 * p; m < 2 * p + 2; m++) {
      float pr[2], pi[2];
#pragma unroll
      for (int x = 0; x < 2; x++)
#pragma unroll
        for (int q = 0; q <= m; q++) {
          const int ih = 16 * (q >> 1) + 2 * (q & 1) + 4 * j + x, iu = 16 * ((m - q) >> 1) + 2 * ((m - q) & 1) + 4 * j + x;
          pr[x] = q ? fmaf(H[ih], U[iu], pr[x]) : H[ih] * U[iu];
          pi[x] = q ? fmaf(H[ih], U[iu + 8], pi[x]) : H[ih] * U[iu + 8];
          pr[x] = fmaf(-H[ih + 8], U[iu + 8], pr[x]);
          pi[x] = fmaf(H[ih + 8], U[iu], pi[x]);
        }
      a[m & 2][2 * j + (m & 1)] = pack2(pr[0], pr[1]);
      a[(m & 2) + 1][2 * j + (m & 1)] = pack2(pi[0], pi[1]);
    }
}

__device__ __forceinline__ void conv_channel(const FftConst& k, uint32_t sb, int c, int wg, int w, int lane) {
  const uint32_t cb = sb + off_ch(c), bars = sb + OFF_BAR;
  const uint32_t du = desc_lo(cb, 1024), dg = desc_lo(sb + OFF_GT, 16), dz = desc_lo(cb + U_BYTES, 16);
  float U[32], H[32];
  uint32_t a[4][4], e[4][4];
  const float dv = __uint_as_float(lds32(sb + OFF_D + 4 * c));
  wg_fence();
  WgRS<64>::set<HI_SW32>(H, k.f[0], du + 256);
  WgRS<64>::mma<HI_SW32>(H, k.f[1], du + 256 + 32);
  wg_commit();
  wg_wait<0>();
  pin<32>(H);
  twiddle_fwd(a, H, k);
  mbar_wait(bars + 8 * (B_U + (c < 3 ? c : 3)), 0);
  TSM(w == 0 && c < 3, 7 + wg);
  wg_fence();
  WgRS<64>::set<HI_SW32>(U, k.f[0], du);
  WgRS<64>::mma<HI_SW32>(U, k.f[1], du + 32);
  wg_commit();
  g_step(H, a, dg, dg + 64);
  wg_wait<1>();
  pin<32>(U);
  twiddle_fwd(e, U, k);
  wg_fence();
  g_step(U, e, dg, dg + 64);
  wg_wait<0>();
  pin<32>(U);
  pin<32>(H);
#pragma unroll
  for (int j = 0; j < 4; j++) H[4 * (j >> 1) + (j & 1)] += dv;
  float V[32];
#pragma unroll
  for (int p = 0; p < 2; p++) {
    products(a, H, U, p);
    wg_fence();
    WgRS<32>::set<HI_SW64>(V + 16 * p, a[2 * p], dg + 64);
    WgRS<32>::mma<HI_SW64>(V + 16 * p, a[2 * p + 1], dg);
    wg_commit();
  }
  const uint32_t za = cb + U_BYTES + (8 * w + (lane & 7)) * 128 + (((lane >> 3) ^ (lane & 7)) << 4);
  const uint32_t ya = cb + (lane >> 4) * 1024 + (8 * w + (lane & 7)) * 32 + ((((lane >> 3) ^ (lane >> 2)) & 1) << 4);
  wg_sync(1 + wg);
#pragma unroll
  for (int p = 0; p < 2; p++) {
    if (p == 0) wg_wait<1>();
    else wg_wait<0>();
    pin<16>(V + 16 * p);
#pragma unroll
    for (int i = 0; i < 4; i++) {
      const int j = i & 1;
      const float* x = V + 16 * p + 4 * j + (i & 2);
      e[p][i] = pack2(x[8], x[9]);
      e[2 + p][i] = pack2(x[0], x[1]);
      rot(e[p][i], e[2 + p][i], k.ta[1][j], k.tb[1][j]);
    }
    stsm4(za ^ (64 * p), e[p]);
    stsm4((za ^ (64 * p)) + 4096, e[2 + p]);
  }
  fence_async_smem();
  wg_sync(1 + wg);
  wg_fence();
  WgRS<64>::set<HI_SW128>(H, k.fi[0], dz);
#pragma unroll
  for (int ks = 1; ks < 4; ks++) WgRS<64>::mma<HI_SW128>(H, k.fi[ks], dz + 128 * ks);
  wg_commit();
  wg_wait<0>();
  pin<32>(H);
  if (lane == 0) mbar_arrive(bars + 8 * B_CVD);
  TSIF(w == 0, 88 + c);
#pragma unroll
  for (int j = 0; j < 8; j++)
    a[j >> 2][j & 3] = j < 2 ? pack2(H[4 * j], H[4 * j + 1]) : pack2(H[4 * j] + H[4 * j - 6], H[4 * j + 1] + H[4 * j - 5]);
  stsm4(ya, a[0]);
  stsm4(ya + 2048, a[1]);
  fence_async_smem();
  __syncwarp();
}

__device__ __forceinline__ void prep_slab(uint4* res, const uint2* sw, uint32_t sb, int slab, int w, int lane) {
  const int t = lane & 3, tp = (lane & 7) >> 1, pos = 8 * tp + 2 * (((lane >> 3) + tp) & 3) + (lane & 1);
  const uint32_t base = sb + OFF_KVS + slab * KVS_BYTES + pos * 128;
  uint32_t kk[2][4][4], vv[2][4];
  mbar_wait(sb + OFF_BAR + 8 * (B_KV + slab), 0);
#pragma unroll
  for (int h = 0; h < 2; h++) {
#pragma unroll
    for (int j = 0; j < 4; j++) {
      const uint32_t a = base + 128 * j;
      ldsm4t(kk[h][j], a + (((w + 4 * h) ^ ((a >> 7) & 7)) << 4));
    }
    const uint32_t a = base + KVS_V;
    ldsm4t(vv[h], a + (((w + 4 * h) ^ ((a >> 7) & 7)) << 4));
  }
#pragma unroll
  for (int h = 0; h < 2; h++) {
    uint32_t (&k)[4][4] = kk[h];
    uint32_t (&v)[4] = vv[h];
    const uint32_t w0 = __byte_perm(sw[h].x, 0, 0x1010), w1 = __byte_perm(sw[h].x, 0, 0x3232);
    const uint32_t w2 = __byte_perm(sw[h].y, 0, 0x1010), w3 = __byte_perm(sw[h].y, 0, 0x3232);
#pragma unroll
    for (int m = 0; m < 4; m++)
      v[m] = bmul(badd(badd(badd(bmul(k[0][m], w3), bmul(k[1][m], w2)), bmul(k[2][m], w1)), bmul(k[3][m], w0)), v[m]);
    uint32_t a[4];
#pragma unroll
    for (int m = 0; m < 4; m++) a[m] = (t & 1) ? v[(m + 3) & 3] : v[m];
    res[h] = (t & 2) ? make_uint4(a[2], a[3], a[0], a[1]) : make_uint4(a[0], a[1], a[2], a[3]);
  }
}

__device__ __forceinline__ void prep_gate(const Params& p, uint32_t sb, int b, int w, int lane) {
  uint2 gw[5], x[4][5];
#pragma unroll
  for (int j = 0; j < 5; j++) gw[j] = ldg64(reinterpret_cast<const uint2*>(p.gate_w) + lane + 32 * j);
#pragma unroll
  for (int i = 0; i < 4; i++)
#pragma unroll
    for (int j = 0; j < 5; j++)
      x[i][j] = ldg64(reinterpret_cast<const uint2*>(p.q) + (16 * b + 4 * w + i) * (DIM / 4) + lane + 32 * j);
  float s[4];
#pragma unroll
  for (int i = 0; i < 4; i++) {
    s[i] = 0.f;
#pragma unroll
    for (int j = 0; j < 5; j++) {
      const uint32_t m0 = bmul(x[i][j].x, gw[j].x), m1 = bmul(x[i][j].y, gw[j].y);
      s[i] += (bf_lo(m0) + bf_hi(m0)) + (bf_lo(m1) + bf_hi(m1));
    }
  }
  const bool h = lane & 16, q = lane & 8;
  const float a = (h ? s[2] : s[0]) + __shfl_xor_sync(0xffffffffu, h ? s[0] : s[2], 16);
  const float c = (h ? s[3] : s[1]) + __shfl_xor_sync(0xffffffffu, h ? s[1] : s[3], 16);
  float z = (q ? c : a) + __shfl_xor_sync(0xffffffffu, q ? a : c, 8);
#pragma unroll
  for (int o = 4; o > 0; o >>= 1) z += __shfl_xor_sync(0xffffffffu, z, o);
  z = bf_lo(pack2(z, 0.f));
  z = bf_lo(pack2(__fdividef(1.f, 1.f + __expf(-z)), 0.f));
  mbar_wait(sb + OFF_BAR + 8 * B_S3, 0);
  if ((lane & 7) == 0) asm volatile("st.shared.f32 [%0], %1;" ::"r"(sb + OFF_GATE + 64 * (b & 7) + 16 * w + (lane >> 1)), "f"(z) : "memory");
  fence_async_smem();
}

__device__ __forceinline__ uint32_t bmax(uint32_t a, uint32_t b) {
  uint32_t d;
  asm("max.bf16x2 %0, %1, %2;" : "=r"(d) : "r"(a), "r"(b));
  return d;
}
__device__ __forceinline__ void softmax_two(const float (&l)[2][2], uint32_t& p0, uint32_t& p1) {
  constexpr float kScale = 0.22360679774997896f, kLog2e = 1.4426950408889634f;
  const uint32_t r0 = pack2(l[0][0], l[1][0]), r1 = pack2(l[0][1], l[1][1]);
  const uint32_t x0 = pack2(bf_lo(r0) * kScale, bf_hi(r0) * kScale), x1 = pack2(bf_lo(r1) * kScale, bf_hi(r1) * kScale);
  uint32_t m = bmax(x0, x1);
  m = bmax(m, __shfl_xor_sync(0xffffffffu, m, 1));
  m = bmax(m, __shfl_xor_sync(0xffffffffu, m, 2));
  const float m0 = bf_lo(m) * kLog2e, m1 = bf_hi(m) * kLog2e;
  p0 = pack2(ex2(bf_lo(x0) * kLog2e - m0), ex2(bf_lo(x1) * kLog2e - m0));
  p1 = pack2(ex2(bf_hi(x0) * kLog2e - m1), ex2(bf_hi(x1) * kLog2e - m1));
}

__device__ __forceinline__ void halo_read(uint32_t (&kpv)[10], uint32_t (&vpv)[10], uint32_t (&tg)[7], const uint4* hp) {
#pragma unroll
  for (int j = 0; j < 7; j++) {
    uint32_t x0, x1, x2;
    asm volatile("ld.relaxed.gpu.global.v4.u32 {%0, %1, %2, %3}, [%4];"
                 : "=r"(x0), "=r"(x1), "=r"(x2), "=r"(tg[j]) : "l"(hp + 32 * j) : "memory");
    if (j < 4) kpv[3 * j] = x0; else vpv[3 * j - 10] = x0;
    if (j < 3) kpv[3 * j + 1] = x1; else vpv[3 * j - 9] = x1;
    if (j < 3) kpv[3 * j + 2] = x2; else if (j < 6) vpv[3 * j - 8] = x2;
  }
}

template <int ROT>
__device__ __forceinline__ void pack_qkv(const float* acc, uint32_t (&qlo)[10], uint32_t (&qhi)[10], uint32_t (&klo)[10],
                                         uint32_t (&khi)[10], uint32_t (&vlo)[10], uint32_t (&vhi)[10]) {
#pragma unroll
  for (int j = 0; j < 10; j++) {
    const int x = (j + ROT) % 10, tq = x < 8 ? x : 16 + x, tk = x < 8 ? 8 + x : 18 + x, tv = x < 8 ? 16 + x : 20 + x;
    khi[j] = pack2(acc[4 * tk + 2], acc[4 * tk + 3]);
    vhi[j] = movm(pack2(acc[4 * tv + 2], acc[4 * tv + 3]));
    qlo[j] = pack2(acc[4 * tq], acc[4 * tq + 1]);
    qhi[j] = pack2(acc[4 * tq + 2], acc[4 * tq + 3]);
    klo[j] = pack2(acc[4 * tk], acc[4 * tk + 1]);
    vlo[j] = pack2(acc[4 * tv], acc[4 * tv + 1]);
    asm volatile("" : "+r"(khi[j]), "+r"(qlo[j]), "+r"(qhi[j]), "+r"(klo[j]), "+r"(vlo[j]));
  }
}

template <int ROT> __device__ __forceinline__ void halo_send(const float* acc, uint4* ho, uint32_t tag) {
#pragma unroll
  for (int j = 0; j < 7; j++) {
    uint32_t x[3];
#pragma unroll
    for (int e = 0; e < 3; e++) {
      const int i = 3 * j + e, y = (i % 10 + ROT) % 10, tk = y < 8 ? 8 + y : 18 + y, tv = y < 8 ? 16 + y : 20 + y;
      x[e] = i < 10 ? pack2(acc[4 * tk + 2], acc[4 * tk + 3]) : i < 20 ? movm(pack2(acc[4 * tv + 2], acc[4 * tv + 3])) : 0u;
    }
    asm volatile("st.relaxed.gpu.global.v4.u32 [%0], {%1, %2, %3, %4};" ::"l"(ho + 32 * j), "r"(x[0]), "r"(x[1]), "r"(x[2]), "r"(tag) : "memory");
  }
}

__device__ __forceinline__ void attention(float* acc, uint32_t sb, int b, int par, int w, int lane, uint32_t tag, FftConst& fc) {
  const int g = lane >> 2, t = lane & 3;
  uint32_t klo[10], khi[10], vlo[10], vhi[10], qlo[10], qhi[10], kpv[10], vpv[10];
  if (w == 3 && b < NCTA - 8) {
    uint4* ho = g_halo + (b * 2 + par) * 224 + lane;
    if (tail_first(b & 7)) halo_send<8>(acc, ho, tag);
    else halo_send<0>(acc, ho, tag);
    TSIF(par == 0, 76);
    pin<120>(acc);
  }
  if (tail_first(b & 7)) pack_qkv<8>(acc, qlo, qhi, klo, khi, vlo, vhi);
  else pack_qkv<0>(acc, qlo, qhi, klo, khi, vlo, vhi);
  const uint32_t xa = sb + OFF_KVX + (par * 3) * 2560 + lane * 16;
  if (w < 3) {
    sts128(xa + w * 2560, khi[0], khi[1], khi[2], khi[3]);
    sts128(xa + w * 2560 + 512, khi[4], khi[5], khi[6], khi[7]);
    sts128(xa + w * 2560 + 1024, khi[8], khi[9], vhi[0], vhi[1]);
    sts128(xa + w * 2560 + 1536, vhi[2], vhi[3], vhi[4], vhi[5]);
    sts128(xa + w * 2560 + 2048, vhi[6], vhi[7], vhi[8], vhi[9]);
  }
  TSIF(par == 0 && w == 1, 64);
#pragma unroll
  for (int j = 0; j < 10; j++) vlo[j] = movm(vlo[j]);
  const bool far0 = 2 * t > g, far1 = 2 * t + 1 > g;
  const uint32_t mfar = (far0 ? 0x0000FFFFu : 0u) | (far1 ? 0xFFFF0000u : 0u);
  float slo[4][2], lg[2][2];
  uint32_t phi[4], plo[4], qml[4], qmh[4];
#pragma unroll
  for (int h = 0; h < 4; h++) {
    const int f = h == 0 ? 0 : h == 1 ? 3 : h == 2 ? 5 : 8, hf = h < 2 ? 2 : 7;
    const bool mine = (h & 1) ? t >= 2 : t < 2;
    qml[h] = mine ? qlo[hf] : 0u;
    qmh[h] = mine ? qhi[hf] : 0u;
    float a[4] = {0.f, 0.f, 0.f, 0.f}, c[4] = {0.f, 0.f, 0.f, 0.f};
    mma16816(a, qlo[f], qhi[f], qlo[f + 1], qhi[f + 1], klo[f], klo[f + 1]);
    mma16816(c, qlo[f], qhi[f], qlo[f + 1], qhi[f + 1], khi[f], khi[f + 1]);
    mma1688(a, qml[h], qmh[h], klo[hf]);
    mma1688(c, qml[h], qmh[h], khi[hf]);
    slo[h][0] = a[0];
    slo[h][1] = a[1];
    lg[h & 1][0] = far0 ? a[2] : c[2];
    lg[h & 1][1] = far1 ? a[3] : c[3];
    if (h & 1) softmax_two(lg, phi[h - 1], phi[h]);
  }
  TSIF(par == 0 && w == 1, 65);
  wg_sync(1 + par);
  TSIF(par == 0 && w == 1, 66);
  const bool nohist = (w == 0) && (b < 8);
  const uint4* hp = g_halo + ((b - 8) * 2 + par) * 224 + lane;
  uint32_t tg[7];
  if (w > 0) {
    const uint4 v0 = lds128(xa + (w - 1) * 2560), v1 = lds128(xa + (w - 1) * 2560 + 512), v2 = lds128(xa + (w - 1) * 2560 + 1024);
    const uint4 v3 = lds128(xa + (w - 1) * 2560 + 1536), v4 = lds128(xa + (w - 1) * 2560 + 2048);
    kpv[0] = v0.x; kpv[1] = v0.y; kpv[2] = v0.z; kpv[3] = v0.w; kpv[4] = v1.x; kpv[5] = v1.y; kpv[6] = v1.z; kpv[7] = v1.w;
    kpv[8] = v2.x; kpv[9] = v2.y; vpv[0] = v2.z; vpv[1] = v2.w; vpv[2] = v3.x; vpv[3] = v3.y; vpv[4] = v3.z; vpv[5] = v3.w;
    vpv[6] = v4.x; vpv[7] = v4.y; vpv[8] = v4.z; vpv[9] = v4.w;
  } else if (nohist) {
#pragma unroll
    for (int j = 0; j < 10; j++) kpv[j] = vpv[j] = 0u;
  } else {
    TSIF(par == 0, 77);
    halo_read(kpv, vpv, tg, hp);
  }
  if (w == 0 && !nohist) {
    int spins = 0;
    while (true) {
      bool ok = true;
#pragma unroll
      for (int j = 0; j < 7; j++) ok = ok && tg[j] == tag;
      if (__all_sync(0xffffffffu, ok) || ++spins > SPIN_LIMIT) break;
      halo_read(kpv, vpv, tg, hp);
    }
    TSIF(par == 0, 79);
  }
#pragma unroll
  for (int h = 0; h < 4; h++) {
    const int f = h == 0 ? 0 : h == 1 ? 3 : h == 2 ? 5 : 8, hf = h < 2 ? 2 : 7;
    float a[4] = {0.f, 0.f, 0.f, 0.f};
    mma16816(a, qlo[f], qhi[f], qlo[f + 1], qhi[f + 1], kpv[f], kpv[f + 1]);
    mma1688(a, qml[h], qmh[h], kpv[hf]);
    const float ninf = __int_as_float(0xff800000);
    lg[h & 1][0] = far0 ? (nohist ? ninf : a[0]) : slo[h][0];
    lg[h & 1][1] = far1 ? (nohist ? ninf : a[1]) : slo[h][1];
    if (h & 1) softmax_two(lg, plo[h - 1], plo[h]);
  }
  TSIF(par == 0 && w <= 1, 67 + w);
  uint32_t ov[20];
#pragma unroll
  for (int hp = 0; hp < 2; hp++) {
    if (FC_AT == 1 + hp) {
      mbar_wait(sb + OFF_BAR + 8 * B_HA, 0);
      fft_matrices(fc, sb, w, lane);
    }
    const int hf = hp ? 7 : 2;
    float sh[4] = {0.f, 0.f, 0.f, 0.f}, i0 = 0.f, i1 = 0.f;
#pragma unroll
    for (int e = 0; e < 2; e++) {
      const int h = 2 * hp + e, f = h == 0 ? 0 : h == 1 ? 3 : h == 2 ? 5 : 8;
      const uint32_t a0 = plo[h] & mfar, a2 = plo[h] & ~mfar, a3 = phi[h] & mfar, c1 = phi[h] & ~mfar;
      float sum[4] = {0.f, 0.f, 0.f, 0.f};
      mma1688(sum, plo[h], phi[h], 0x3F803F80u);
      const float r0 = rcp(sum[0]), r1 = rcp(sum[2]);
#pragma unroll
      for (int j = f; j < f + 2; j++) {
        float o[4] = {0.f, 0.f, 0.f, 0.f};
        mma16816(o, a0, 0u, a2, a3, vpv[j], vlo[j]);
        mma1688(o, 0u, c1, vhi[j]);
        ov[2 * j] = pack2(o[0] * r0, o[1] * r0);
        ov[2 * j + 1] = pack2(o[2] * r1, o[3] * r1);
      }
      const bool mine = e ? g >= 4 : g < 4;
      mma16816(sh, a0, 0u, a2, a3, mine ? vpv[hf] : 0u, mine ? vlo[hf] : 0u);
      mma1688(sh, 0u, c1, mine ? vhi[hf] : 0u);
      if (e == 0 || t >= 2) {
        i0 = r0;
        i1 = r1;
      }
    }
    ov[2 * hf] = pack2(sh[0] * i0, sh[1] * i0);
    ov[2 * hf + 1] = pack2(sh[2] * i1, sh[3] * i1);
  }
  TS(32 + 4 * par + w);
  if (FC_AT == 3) {
    mbar_wait(sb + OFF_BAR + 8 * B_HA, 0);
    fft_matrices(fc, sb, w, lane);
  }
  mbar_wait(sb + OFF_BAR + 8 * B_P1, 0);
  const uint32_t oa = sb + OFF_OA + (lane >> 4) * 2048 + (32 * w + 2 * (lane & 15) + par) * 16;
#pragma unroll
  for (int j = 0; j < 5; j++) stsm4(oa + 4096 * j, ov + 4 * j);
  TSIF(par == 0 && w == 0, 120);
  fence_async_smem();
  TSIF(par == 0 && w == 0, 121);
  __syncwarp();
  if (lane == 0) mbar_arrive(sb + OFF_BAR + 8 * B_ATTN);
  TSM(w == 0 || w == 2, 122 + par + (w == 2 ? 3 : 0));
}

struct Maps {
  CUtensorMap x, wm, wt, k, v, y, wo, qm, qt, om, ot, yl, ol, wh;
};

__device__ __forceinline__ void load_stage(uint32_t sb, int kb, int b, const Maps& m) {
  const uint32_t st = sb + (kb & 3) * STAGE_BYTES, bar = sb + OFF_BAR + 8 * (B_FULL1 + (kb & 3));
  const int r = b >> 3, hg = b & 7, slab = kb - KV_KB;
  const bool kv = slab >= 0 && slab < 5;
  const uint32_t kbar = sb + OFF_BAR + 8 * (B_KV + slab), dst = sb + OFF_KVS + slab * KVS_BYTES;
  mbar_expect_tx(bar, STAGE_BYTES);
  if (kv) mbar_expect_tx(kbar, KVS_BYTES);
  tma_3d(st, &m.x, 64 * kb, 64 * r, 0, bar);
  tma_3d(st + ST_W, &m.wm, 80 * hg + (tail_first(hg) ? 16 : 0), 64 * kb, 0, bar);
  tma_3d(st + ST_WT, &m.wt, 80 * hg + (tail_first(hg) ? 0 : 64), 64 * kb, 0, bar);
  if (kv) tma_3d(dst, &m.k, 0, 32 * (b >> 1) - 3, 2 * slab + (b & 1), kbar);
  if (kv) tma_3d(dst + KVS_V, &m.v, 0, 32 * (b >> 1), 2 * slab + (b & 1), kbar);
}

__global__ void __launch_bounds__(NTHR, 1) fused_kernel(const __grid_constant__ Maps m, const Params p) {
  extern __shared__ __align__(1024) uint8_t smem[];
  const uint32_t sb = (uint32_t)__cvta_generic_to_shared(smem);
  const uint32_t bars = sb + OFF_BAR;
  const int tid = threadIdx.x, lane = tid & 31;
  int b = blockIdx.x;
  b = (((b & 63) >> 3) * 2 + (b & 1)) * 8 + (((b < 64 ? 0x6521 : 0x7430) >> (4 * ((b >> 1) & 3))) & 7);
  const int r = b >> 3, hg = b & 7;

  if (tid == T_ISSUE) {
    TSM(true, 0);
#pragma unroll
    for (int i = 0; i < 4; i++) mbar_init(bars + 8 * (B_F0 + i), 1);
    fence_async_smem();
#pragma unroll
    for (int i = 0; i < 4; i++) {
      mbar_expect_tx(bars + 8 * (B_F0 + i), (i ? 0 : ST_W) + 6144);
      if (i == 0) tma_3d(sb, &m.x, 0, 64 * r, 0, bars + 8 * B_F0);
      tma_3d(sb + ST_W + 6144 * i, &m.wh, 80 * hg + (tail_first(hg) ? 16 : 0), 16 * i, 0, bars + 8 * (B_F0 + i));
    }
#pragma unroll
    for (int i = 0; i < 4; i++) mbar_init(bars + 8 * (B_FULL1 + i), 1);
    fence_async_smem();
    mbar_expect_tx(bars + 8 * B_FULL1, STAGE_BYTES - ST_WT);
    tma_3d(sb + ST_WT, &m.wt, 80 * hg + (tail_first(hg) ? 0 : 64), 0, 0, bars + 8 * B_FULL1);
    load_stage(sb, 1, b, m);
  } else if (tid == T_INIT) {
#pragma unroll
    for (int i = 0; i < B_F0; i++) mbar_init(bars + 8 * i, i < B_GATE ? 8 : i < B_CVD ? 4 : i == B_CVD ? 20 : 1);
    fence_async_smem();
  }
  const int warp = __shfl_sync(0xffffffffu, tid >> 5, 0), wg = warp >> 2, w = warp & 3;
  __syncthreads();

  if (wg == 3) {
    asm volatile("setmaxnreg.dec.sync.aligned.u32 56;");
    if (w == 0) {
      if (lane == 0) {
#pragma unroll 1
        for (int kb = 2; kb < 10; kb++) {
          if (kb >= 4) mbar_wait(bars + 8 * (kb == 7 ? B_E3 : B_EMPTY1 + (kb & 3)), (kb >> 3) & 1);
          TSIF(kb >= 4, 44 + kb);
          load_stage(sb, kb, b, m);
          TSIF(kb == 3, 60);
          if (kb == 9) mbar_arrive(bars + 8 * B_LAST);
        }
        mbar_wait(bars + 8 * B_WOP, 0);
        mbar_wait(bars + 8 * B_EPOCH, 0);
        flag_wait(g_cnt + C_W + 32 * hg, (lds32(sb + OFF_EPOCH) + 1) * 16);
        TS(30);
#pragma unroll 1
        for (int j = 0; j < 8; j++) {
          if (j >= 6) mbar_wait(bars + 8 * (B_EMPTY2 + j - 6), 0);
          if (j == 4) mbar_wait(bars + 8 * B_ORB, 0);
          TSIF(j >= 6, 100 + j);
          mbar_expect_tx(bars + 8 * (B_FULL2 + j), j == 0 ? WO_BYTES : j == 5 ? O_BYTES + WO_BYTES + 512 : O_BYTES + WO_BYTES);
          bulk_load(sb + off_w(j), g_WO + (hg * 8 + step_src(hg, j)) * 800, WO_BYTES, bars + 8 * (B_FULL2 + j));
        }
        mbar_wait(bars + 8 * (B_EMPTY2 + 3), 0);
        mbar_expect_tx(bars + 8 * B_QF, O_BYTES);
        tma_2d(sb + OFF_QS, &m.qm, 80 * hg, 128 * r, bars + 8 * B_QF);
        tma_2d(sb + OFF_QT, &m.qt, 80 * hg + 64, 128 * r, bars + 8 * B_QF);
      }
    } else if (w == 1) {
      unsigned epoch = 0;
      if (lane == 0) {
        epoch = atomicAdd(g_cnt + C_LAUNCH, 1u) / NCTA;
        asm volatile("st.shared.u32 [%0], %1;" ::"r"(sb + OFF_EPOCH), "r"(epoch) : "memory");
        mbar_arrive(bars + 8 * B_EPOCH);
        mbar_wait(bars + 8 * B_KVD, 0);
        mbar_expect_tx(bars + 8 * B_HB, 5 * 4096);
#pragma unroll 1
        for (int c = 0; c < 5; c++) {
          if (c == 3) mbar_wait(bars + 8 * B_S3, 0);
          bulk_load(sb + off_ch(c) + U_BYTES, p.ssm_k + (5 * b + c) * SEQ, 4096, bars + 8 * B_HB);
        }
#pragma unroll
        for (int c = 0; c < 4; c++) mbar_expect_tx(bars + 8 * (B_U + c), c < 3 ? U_BYTES : 2 * U_BYTES);
        const uint4* usrc = g_U + 5 * b * U_PITCH;
        mbar_wait(bars + 8 * B_USIG, 0);
        flag_wait(g_cnt + C_PREP + 32 * (b & 15), (epoch + 1) * NCTA);
        TS(23);
#pragma unroll
        for (int c = 0; c < 5; c++) {
          if (c == 3) mbar_wait(bars + 8 * (B_U + 2), 0);
          bulk_load(sb + off_ch(c), usrc + c * U_PITCH, U_BYTES, bars + 8 * (B_U + (c < 3 ? c : 3)));
          TSIF(c == 0 || c == 4, 116 + (c >> 2));
        }
      }
      epoch = __shfl_sync(0xffffffffu, epoch, 0);
      if (lane < 8) {
        const int src = (b & ~7) | step_src(hg, lane);
        mbar_wait(bars + 8 * B_ATTN, 0);
        TS(20);
        bool seen = false;
#pragma unroll 1
        for (int spins = 0; spins < SPIN_LIMIT; spins++) {
          const bool now = !seen && (int)(flag_read(g_cnt + C_O + 32 * src) - (epoch + 1)) >= 0;
          if (now && lane >= 1 && lane < 4) bulk_load(sb + off_o(lane), g_O + src * 1280, O_BYTES, bars + 8 * (B_FULL2 + lane));
          seen = seen || now;
          if (__all_sync(0xff, seen)) break;
        }
        TS(21);
        if (lane == 5) bulk_load(sb + OFF_GATE, g_gate + 128 * r, 512, bars + 8 * (B_FULL2 + 5));
#pragma unroll 1
        for (int j = 4; j < 8; j++) {
          if (lane == j) {
            mbar_wait(bars + 8 * (j < 6 ? B_C34 : B_EMPTY2 + j - 6), 0);
            bulk_load(sb + off_o(j), g_O + src * 1280, O_BYTES, bars + 8 * (B_FULL2 + j));
          }
          __syncwarp(0xff);
        }
        TS(22);
      }
    } else if (w == 2) {
      mbar_wait(bars + 8 * B_PREP, 0);
      flag_signal(g_cnt + C_PREP, 16, lane);
      TS(25);
      if (lane == 0) {
        mbar_arrive(bars + 8 * B_USIG);
        mbar_expect_tx(bars + 8 * B_ORB, O_BYTES / 4 + 64);
        mbar_wait(bars + 8 * B_GATE, 0);
        publish(g_gate + 16 * b, sb + OFF_GATE + 64 * hg, 64);
        bulk_load(sb + OFF_GATE + 64 * hg, g_gate + 16 * b, 64, bars + 8 * B_ORB);
        mbar_wait(bars + 8 * B_ATTN, 0);
        publish(g_O + b * 1280, sb + OFF_OA, O_BYTES);
        tma_2d(sb + OFF_KVX + 10240, &m.ol, 48, b * 160, bars + 8 * B_ORB);
        TS(74);
        mbar_wait(bars + 8 * B_ORB, 0);
        flag_bump(g_cnt + C_O + 32 * b);
        TS(26);
      }
    } else {
      if (lane == 0) {
        uint4* dst = g_WO + (hg * 8 + (r >> 1)) * 800 + (r & 1) * 80;
        mbar_wait(bars + 8 * B_S3, 0);
        asm volatile("cp.async.bulk.prefetch.L2.global [%0], 6400;" ::"l"(p.wo + b * 3200) : "memory");
        mbar_wait(bars + 8 * B_P1, 0);
        mbar_wait(bars + 8 * WB_TRIG, 0);
        mbar_expect_tx(bars + 8 * B_WST, WO_BYTES / 2);
        tma_3d(sb + OFF_WA, &m.wo, 0, 40 * r, 5 * hg, bars + 8 * B_WST);
        mbar_wait(bars + 8 * B_WST, 0);
#pragma unroll 1
        for (int n = 0; n < 5; n++) bulk_store(dst + 160 * n, sb + OFF_WA + 1280 * n, 1280);
        bulk_wait_read();
        mbar_expect_tx(bars + 8 * B_WST, WO_BYTES / 2);
#pragma unroll 1
        for (int n = 0; n < 5; n++) bulk_load(sb + OFF_WA + 1280 * n, dst + 160 * n, 1280, bars + 8 * B_WST);
        mbar_wait(bars + 8 * B_WST, 1);
        flag_bump(g_cnt + C_W + 32 * hg);
        mbar_arrive(bars + 8 * B_WOP);
        TS(71);
        mbar_expect_tx(bars + 8 * B_C34, 3 * (U_BYTES / 4));
        mbar_expect_tx(bars + 8 * B_YRB, 2 * (U_BYTES / 4));
#pragma unroll 1
        for (int c = 0; c < 5; c++) {
          mbar_wait(bars + 8 * (B_YST + c), 0);
          publish(g_U + (5 * b + c) * U_PITCH, sb + off_ch(c), U_BYTES);
          tma_2d(sb + off_ch(c), &m.yl, 48, (5 * b + c) * (U_PITCH / 8), bars + 8 * (c < 3 ? B_C34 : B_YRB));
        }
        TS(75);
        mbar_wait(bars + 8 * B_C34, 0);
        mbar_wait(bars + 8 * B_YRB, 0);
        flag_bump(g_cnt + C_Y + 32 * (b >> 4));
        TS(27);
        mbar_expect_tx(bars + 8 * B_YFULL, 20480);
        flag_wait(g_cnt + C_Y + 32 * hg, (lds32(sb + OFF_EPOCH) + 1) * 16);
        TS(24);
        tma_2d(sb + OFF_YT, &m.y, 128 * r, 80 * hg, bars + 8 * B_YFULL);
        tma_2d(sb + OFF_YT + 10240, &m.y, 128 * r + 64, 80 * hg, bars + 8 * B_YFULL);
      }
    }
  } else {
    asm volatile("setmaxnreg.inc.sync.aligned.u32 152;");
    FftConst fc;
    if (wg < 2) {
      float acc[120];
#pragma unroll
      for (int i = 0; i < 120; i++) acc[i] = 0.f;
      const uint32_t da = desc_lo(sb + wg * 8192, 16), db = desc_lo(sb + ST_W, 8192), dc = desc_lo(sb + ST_WT, 2048);
#pragma unroll
      for (int k = 0; k < 4; k++) {
        mbar_wait(bars + 8 * (B_F0 + k), 0);
        TSIF(w == 0 && wg == 0 && k == 0, 1);
        wg_fence();
        WgSST<192>::mma<HI_SW128, HI_SW128>(acc, da + 2 * k, desc_lo(sb + ST_W, 2048) + 384 * k, 1);
        wg_commit();
      }
      mbar_wait(bars + 8 * B_FULL1, 0);
      wg_fence();
#pragma unroll
      for (int k = 0; k < 4; k++) WgSST<48>::mma<HI_SW128, HI_SW32>(acc + 96, da + 2 * k, dc + 32 * k, 1);
      wg_commit();
#pragma unroll 1
      for (int kb = 1; kb < 10; kb++) {
        mbar_wait(bars + 8 * (B_FULL1 + (kb & 3)), (kb >> 2) & 1);
        const uint32_t so = (kb & 3) * (STAGE_BYTES >> 4);
        wg_fence();
#pragma unroll
        for (int k = 0; k < 4; k++) {
          WgSST<192>::mma<HI_SW128, HI_SW128>(acc, da + so + 2 * k, db + so + 128 * k, 1);
          WgSST<48>::mma<HI_SW128, HI_SW32>(acc + 96, da + so + 2 * k, dc + so + 32 * k, 1);
        }
        wg_commit();
        wg_wait<1>();
        if (lane == 0) mbar_arrive(bars + 8 * (kb == 4 ? B_E3 : B_EMPTY1 + ((kb - 1) & 3)));
      }
      mbar_wait(bars + 8 * B_EPOCH, 0);
      const uint32_t tag = lds32(sb + OFF_EPOCH) + 1;
      mbar_wait(bars + 8 * B_S3, 0);
      wg_wait<0>();
      pin<120>(acc);
      if (lane == 0) mbar_arrive(bars + 8 * B_P1);
      TSM(w == 0, 3 + wg);
      attention(acc, sb, b, wg, w, lane, tag, fc);
    } else {
      const int tw = tid & 127, chl = 64 * (b & 1) + 8 * w + (lane >> 2);
      uint4* up = g_U + chl * U_PITCH + ((4 * (b >> 1) + (lane & 3)) ^ ((b >> 2) & 1));
      uint2 sw[10];
      uint32_t dv = 0;
      if (lane < 5) dv = __ldg(reinterpret_cast<const unsigned short*>(p.ssm_D) + 5 * b + lane);
#pragma unroll
      for (int i = 0; i < 10; i++) sw[i] = ldg64(reinterpret_cast<const uint2*>(p.shift_k) + chl + 128 * (i >> 1) + 32 * (i & 1));
      uint32_t tab[12];
      uint32_t tt[2];
      fft_tables(tab, tw);
      fft_twiddles(tt, tw);
      uint4 res[10];
#pragma unroll
      for (int i = 0; i < 10; i++) res[i] = make_uint4(0, 0, 0, 0);
#pragma unroll 1
      for (int slab = 0; slab < 5; slab++) {
#pragma unroll
        for (int i = 0; i < 8; i++) res[i] = res[i + 2];
        prep_slab(res + 8, sw, sb, slab, w, lane);
        TSIF(w == 0, 99 + 4 * slab);
#pragma unroll
        for (int i = 0; i < 8; i++) sw[i] = sw[i + 2];
      }
      TSIF(w == 0, 28);
      __syncwarp();
      if (lane == 0) mbar_arrive(bars + 8 * B_KVD + ((res[8].x ^ res[9].x) & p.zero));
      mbar_wait(bars + 8 * B_KVD, 0);
      fft_tables_store(tab, sb, tw);
      mbar_wait(bars + 8 * B_LAST, 0);
#pragma unroll
      for (int i = 0; i < 10; i++) up[(128 * (i >> 1) + 32 * (i & 1)) * U_PITCH] = res[i];
      __syncwarp();
      if (lane == 0) mbar_arrive(bars + 8 * B_PREP);
      TSIF(w == 0, 5);
      mbar_wait(bars + 8 * B_LAST, 0);
      prep_gate(p, sb, b, w, lane);
      __syncwarp();
      if (lane == 0) mbar_arrive(bars + 8 * B_GATE);
      TSIF(w == 0, 72);
      mbar_wait(bars + 8 * B_HB, 0);
      TSIF(w == 0, 2);
      const uint32_t ha = sb + U_BYTES + ((tw >> 3) * 16 + 8 + (tw & 7)) * 16;
      uint4 hv[5];
#pragma unroll
      for (int c = 0; c < 5; c++) hv[c] = lds128(ha + off_ch(c));
      __syncwarp();
#pragma unroll
      for (int c = 0; c < 5; c++) sts128((ha ^ 16) + off_ch(c), hv[c].x, hv[c].y, hv[c].z, hv[c].w);
      asm volatile("st.shared.v2.u32 [%0], {%1, %2};" ::"r"(sb + OFF_TT + 8 * tw), "r"(tt[0]), "r"(tt[1]) : "memory");
      if (tw < 5) asm volatile("st.shared.f32 [%0], %1;" ::"r"(sb + OFF_D + 4 * tw), "f"(bf_lo(dv) * 0.125f) : "memory");
      fence_async_smem();
      __syncwarp();
      if (lane == 0) mbar_arrive(bars + 8 * B_HA);
      TSIF(w == 0, 6);
      if (FC_AT) {
        mbar_wait(bars + 8 * B_HA, 0);
        fft_matrices(fc, sb, w, lane);
      }
    }

    TSM(w == 0 && wg == 0, 104);
    if (!FC_AT) {
      mbar_wait(bars + 8 * B_HA, 0);
      fft_matrices(fc, sb, w, lane);
    }
    TSM(w == 0 && wg == 0, 105);
    TSM(w == 0 && wg == 2, 124);
#pragma unroll 1
    for (uint32_t tasks = wg == 0 ? TASK0 : wg == 1 ? TASK1 : TASK2; tasks; tasks >>= 4) {
      const int c = (tasks & 7) - 1;
      conv_channel(fc, sb, c, wg, w, lane);
      if (lane == 0) mbar_arrive(bars + 8 * (B_YST + c));
      TSM(w == 0, 10 + c);
    }

    if (wg != 1) {
      const int wg = warp >> 3;
      const int g = lane >> 2;
      float acc[40];
#pragma unroll
      for (int i = 0; i < 40; i++) acc[i] = 0.f;
      const uint32_t da = desc_lo(sb + wg * 1024, 2048), db = desc_lo(sb, 2560);
      mbar_wait(bars + 8 * B_ORB, 0);
      mbar_wait(bars + 8 * B_FULL2, 0);
      TSM(w == 0, 15 + wg);
#pragma unroll 1
      for (int j = 0; j < 8; j++) {
        if (j == 1 - wg) mbar_wait(bars + 8 * B_CVD, 0);
        mbar_wait(bars + 8 * (B_FULL2 + j), 0);
        TSM(w == 0 && wg == 0, 44 + (j < 4 ? j : j + 6));
        const uint32_t oa = da + (off_o(j) >> 4), ob = db + (off_w(j) >> 4);
        wg_fence();
#pragma unroll
        for (int k = 0; k < 5; k++) WgSST<80>::mma<HI_NONE, HI_SW32>(acc, oa + 256 * k, ob + 32 * k, 1);
        wg_commit();
        wg_wait<1>();
        if (j >= 1 && j <= 4 && lane == 0) mbar_arrive(bars + 8 * (B_EMPTY2 + j - 1));
      }
      TSIF(w == 0 && wg == 0, 113);
      const int tr = 64 * wg + 16 * w + (lane & 15);
      const uint32_t fm = sb + OFF_QS + tr * 128, fx = (lane >> 4) ^ (tr & 7);
      const uint32_t ft = sb + OFF_QT + tr * 32 + (((lane >> 4) ^ (tr >> 2)) & 1) * 16;
      const float g0 = __uint_as_float(lds32(sb + OFF_GATE + (64 * wg + 16 * w + g) * 4));
      const float g1 = __uint_as_float(lds32(sb + OFF_GATE + (64 * wg + 16 * w + 8 + g) * 4));
      const uint32_t ga = pack2(g0, g0), gb = pack2(g1, g1);
      const uint32_t na = pack2(1.f - g0, 1.f - g0), nb = pack2(1.f - g1, 1.f - g1);

      uint32_t qf[20];
      mbar_wait(bars + 8 * B_QF, 0);
      TSM(w == 0 && wg == 0, 99);
#pragma unroll
      for (int j = 0; j < 5; j++) ldsm4(qf + 4 * j, j < 4 ? fm + ((fx ^ (2 * j)) << 4) : ft);
#pragma unroll
      for (int i = 0; i < 20; i++) {
        qf[i] = bmul((i & 1) ? gb : ga, qf[i]);
        asm volatile("" : "+r"(qf[i]));
      }

      wg_wait<0>();
      pin<40>(acc);
      TSM(w == 0, 17 + wg);
      uint32_t pb[20];
#pragma unroll
      for (int j = 0; j < 10; j++) {
        pb[2 * j] = bmul(na, pack2(acc[4 * j], acc[4 * j + 1]));
        pb[2 * j + 1] = bmul(nb, pack2(acc[4 * j + 2], acc[4 * j + 3]));
        asm volatile("" : "+r"(pb[2 * j]), "+r"(pb[2 * j + 1]));
      }
      const uint32_t ya = sb + OFF_YT + wg * 10240 + ((lane >> 4) * 8 + (lane & 7)) * 128 +
                          (((2 * w + (((lane >> 3) & 1) ^ wg)) ^ (lane & 7)) << 4);
      mbar_wait(bars + 8 * B_YFULL, 0);
      TSM(w == 0 && wg == 0, 19);
#pragma unroll
      for (int j = 0; j < 5; j++) {
        uint32_t y[4];
        ldsm4t(y, ya + 2048 * j);
#pragma unroll
        for (int i = 0; i < 4; i++)
          qf[4 * j + i] = bfma(qf[4 * j + i], y[i], pb[4 * j + i]);
      }
#pragma unroll
      for (int j = 0; j < 5; j++) stsm4(j < 4 ? fm + ((fx ^ (2 * j)) << 4) : ft, qf + 4 * j);
      fence_async_smem();
      __syncwarp();
      if (lane == 0) {
        const int row = 64 * wg + 16 * w;
        asm volatile("cp.async.bulk.tensor.2d.global.shared::cta.bulk_group [%0, {%2, %3}], [%1];"
                     ::"l"(&m.om), "r"(sb + OFF_QS + row * 128), "r"(80 * hg), "r"(128 * r + row) : "memory");
        asm volatile("cp.async.bulk.tensor.2d.global.shared::cta.bulk_group [%0, {%2, %3}], [%1];"
                     ::"l"(&m.ot), "r"(sb + OFF_QT + row * 32), "r"(80 * hg + 64), "r"(128 * r + row) : "memory");
        asm volatile("cp.async.bulk.commit_group;\ncp.async.bulk.wait_group.read 0;" ::: "memory");
      }
      TSM(w == 0 || w == 3, 40 + 2 * wg + (w & 1));
    }
  }
}

typedef CUresult (*EncodeFn)(CUtensorMap*, CUtensorMapDataType, cuuint32_t, void*, const cuuint64_t*, const cuuint64_t*,
                             const cuuint32_t*, const cuuint32_t*, CUtensorMapInterleave, CUtensorMapSwizzle,
                             CUtensorMapL2promotion, CUtensorMapFloatOOBfill);

void encode(EncodeFn fn, CUtensorMap* tm, const void* base, int rank, const cuuint64_t* dims, const cuuint64_t* strides,
            const cuuint32_t* box, CUtensorMapSwizzle swz) {
  const cuuint32_t ones[3] = {1, 1, 1};
  fn(tm, CU_TENSOR_MAP_DATA_TYPE_BFLOAT16, rank, const_cast<void*>(base), dims, strides, box, ones,
     CU_TENSOR_MAP_INTERLEAVE_NONE, swz, CU_TENSOR_MAP_L2_PROMOTION_L2_128B, CU_TENSOR_MAP_FLOAT_OOB_FILL_NONE);
}

}

extern "C" void kernel_launch(void* const* d_in, const int* in_sizes, int n_in, void* d_out, int out_size) {
  (void)in_sizes; (void)n_in; (void)out_size;
  Params p;
  p.q = (const __nv_bfloat16*)d_in[0];
  p.k = (const __nv_bfloat16*)d_in[1];
  p.v = (const __nv_bfloat16*)d_in[2];
  p.shift_k = (const __nv_bfloat16*)d_in[3];
  p.ssm_k = (const __nv_bfloat16*)d_in[4];
  p.ssm_D = (const __nv_bfloat16*)d_in[5];
  p.wqkv = (const __nv_bfloat16*)d_in[7];
  p.wo = (const __nv_bfloat16*)d_in[8];
  p.gate_w = (const __nv_bfloat16*)d_in[9];
  p.out = (__nv_bfloat16*)d_out;
  p.zero = 0;

  static EncodeFn fn = nullptr;
  static void *yaddr = nullptr, *oaddr = nullptr;
  if (!fn) {
    cudaDriverEntryPointQueryResult qr;
    void* f = nullptr;
    cudaGetDriverEntryPoint("cuTensorMapEncodeTiled", &f, cudaEnableDefault, &qr);
    fn = (EncodeFn)f;
    cudaGetSymbolAddress(&yaddr, g_U);
    cudaGetSymbolAddress(&oaddr, g_O);
    cudaFuncSetAttribute(fused_kernel, cudaFuncAttributeMaxDynamicSharedMemorySize, SMEM_BYTES);
  }
  Maps m;
  {
    const cuuint64_t dims[3] = {640, 1024, 2}, st[2] = {2560, 1280};
    const cuuint32_t box[3] = {64, 64, 2};
    encode(fn, &m.x, p.q, 3, dims, st, box, CU_TENSOR_MAP_SWIZZLE_128B);
  }
  {
    const cuuint64_t dims[3] = {640, 640, 3}, st[2] = {3840, 1280};
    const cuuint32_t box[3] = {64, 64, 3}, boxt[3] = {16, 64, 3};
    encode(fn, &m.wm, p.wqkv, 3, dims, st, box, CU_TENSOR_MAP_SWIZZLE_128B);
    encode(fn, &m.wt, p.wqkv, 3, dims, st, boxt, CU_TENSOR_MAP_SWIZZLE_32B);
    const cuuint32_t boxh[3] = {64, 16, 3};
    encode(fn, &m.wh, p.wqkv, 3, dims, st, boxh, CU_TENSOR_MAP_SWIZZLE_128B);
  }
  {
    const cuuint64_t dims[3] = {64, 2048, 10}, st[2] = {1280, 128};
    const cuuint32_t boxk[3] = {64, 35, 1}, boxv[3] = {64, 32, 1};
    encode(fn, &m.k, p.k, 3, dims, st, boxk, CU_TENSOR_MAP_SWIZZLE_128B);
    encode(fn, &m.v, p.v, 3, dims, st, boxv, CU_TENSOR_MAP_SWIZZLE_128B);
  }
  {
    const cuuint64_t dims[3] = {16, 640, 40}, st[2] = {1280, 32};
    const cuuint32_t box[3] = {16, 40, 5};
    encode(fn, &m.wo, p.wo, 3, dims, st, box, CU_TENSOR_MAP_SWIZZLE_32B);
  }
  {
    const cuuint64_t dims[2] = {2048, 640}, st[1] = {U_PITCH * 16};
    const cuuint32_t box[2] = {64, 80};
    encode(fn, &m.y, yaddr, 2, dims, st, box, CU_TENSOR_MAP_SWIZZLE_128B);
    const cuuint64_t dl[2] = {64, DIM * U_PITCH / 8}, dol[2] = {64, NCTA * 160}, sl[1] = {128};
    const cuuint32_t bl[2] = {16, 32}, bol[2] = {16, 160};
    encode(fn, &m.yl, yaddr, 2, dl, sl, bl, CU_TENSOR_MAP_SWIZZLE_NONE);
    encode(fn, &m.ol, oaddr, 2, dol, sl, bol, CU_TENSOR_MAP_SWIZZLE_NONE);
  }
  {
    const cuuint64_t dims[2] = {640, 2048}, st[1] = {1280};
    const cuuint32_t bqm[2] = {64, 128}, bqt[2] = {16, 128}, bom[2] = {64, 16}, bot[2] = {16, 16};
    encode(fn, &m.qm, p.q, 2, dims, st, bqm, CU_TENSOR_MAP_SWIZZLE_128B);
    encode(fn, &m.qt, p.q, 2, dims, st, bqt, CU_TENSOR_MAP_SWIZZLE_32B);
    encode(fn, &m.om, p.out, 2, dims, st, bom, CU_TENSOR_MAP_SWIZZLE_128B);
    encode(fn, &m.ot, p.out, 2, dims, st, bot, CU_TENSOR_MAP_SWIZZLE_32B);
  }
  fused_kernel<<<NCTA, NTHR, SMEM_BYTES>>>(m, p);
}
```

```cpp
#include <cuda.h>
#include <cuda_bf16.h>
#include <cuda_runtime.h>
#include <stdint.h>

namespace {

constexpr int SEQ = 2048, DIM = 640, NCTA = 128, NTHR = 512;

#define KV_KB 2
#define DEV_EXIT 0
#define FENCE_LO 0
#define FENCE_HI 0
#define WB_TRIG B_USIG
#define T_ISSUE 288
#define FC_AT 1
#define T_INIT 448
#define TASK0 0x3
#define TASK1 0x52
#define TASK2 0x41

constexpr uint32_t STAGE_BYTES = 47104, ST_W = 16384, ST_WT = 40960;
constexpr uint32_t O_BYTES = 20480, WO_BYTES = 12800;
constexpr uint32_t OFF_OA = 0;
constexpr uint32_t OFF_QS = 3 * O_BYTES, OFF_QT = OFF_QS + 16384;
constexpr uint32_t OFF_WC = 81920;
constexpr uint32_t OFF_WA = 94720;
constexpr uint32_t OFF_GATE = 145920;
constexpr uint32_t OFF_TT = 146432;
constexpr uint32_t OFF_KVX = 148480;
constexpr uint32_t OFF_CH3 = 163840;
constexpr uint32_t CH_BYTES = 12288, U_BYTES = 4096;
constexpr uint32_t OFF_FT = 225280, OFF_GT = 229376;
constexpr uint32_t OFF_CH0 = 188416;
constexpr uint32_t OFF_KVS = OFF_CH0, KVS_V = 4480, KVS_BYTES = 8576;
constexpr uint32_t OFF_YT = 163840;
constexpr uint32_t OFF_BAR = 231936;
constexpr uint32_t SMEM_BYTES = OFF_BAR + 512;

enum : uint32_t {
  B_EMPTY1 = 0, B_S3 = 3, B_E3 = 4, B_EMPTY2 = 5, B_ATTN = 9, B_P1 = 10,
  B_GATE = 11, B_HA = 12, B_KVD = 13, B_PREP = 14, B_YST = 15,
  B_CVD = 20,
  B_FULL2 = 21, B_U = 29, B_KV = 33, B_HB = 38, B_C34 = 39, B_YRB = 40, B_YFULL = 41, B_EPOCH = 42, B_LAST = 43,
  B_WOP = 44, B_USIG = 45, B_WST = 46, B_QF = 47, B_ORB = 48,
  B_F0 = 49, B_FULL1 = 53
};
constexpr uint32_t OFF_EPOCH = OFF_BAR + 8 * 58, OFF_D = OFF_BAR + 8 * 60;
__device__ __forceinline__ uint32_t off_o(int j) { return j < 4 ? OFF_OA + j * O_BYTES : j < 6 ? OFF_CH0 + (j - 4) * O_BYTES : OFF_OA + (j - 6) * O_BYTES; }
__device__ __forceinline__ uint32_t off_w(int j) { return j < 4 ? OFF_WA + j * WO_BYTES : j == 4 ? OFF_KVX : j == 5 ? OFF_WC : OFF_WA + (j - 6) * WO_BYTES; }
__device__ __forceinline__ int step_src(int hg, int j) { return j == 0 ? hg : j <= hg ? j - 1 : j; }
__device__ __forceinline__ bool tail_first(int hg) { return (hg & 3) == 3; }
__device__ __forceinline__ uint32_t off_ch(int c) { return (c < 3 ? OFF_CH0 : OFF_CH3 - 3 * CH_BYTES) + c * CH_BYTES; }

#define U_PITCH 264
__device__ __align__(1024) uint4 g_U[DIM * U_PITCH];
__device__ __align__(128) uint4 g_O[NCTA * 1280];
__device__ uint4 g_WO[64 * 800];
__device__ uint4 g_halo[NCTA * 2 * 7 * 32];
__device__ __align__(128) float g_gate[SEQ];
__device__ unsigned g_cnt[32 * (1 + 2 * 16 + 8 + NCTA)];
constexpr int C_LAUNCH = 0, C_PREP = 32, C_Y = 32 * 17, C_W = 32 * 33, C_O = 32 * 41;

#define TSM(cond, slot) do { } while (0)
#define TSIF(cond, slot) do { if (__LINE__ >= FENCE_LO && __LINE__ < FENCE_HI) sched_fence(); } while (0)
__device__ __forceinline__ void sched_fence() {
  asm volatile("{\n.reg .pred p;\n.reg .u32 c;\nmov.u32 c, %%clock;\nsetp.eq.u32 p, c, 0;\n@p st.shared.u32 [%0], c;\n}"
               ::"r"(1024 + OFF_EPOCH + 4) : "memory");
}
#define TS(slot) TSIF(true, slot)

struct Params {
  const __nv_bfloat16 *q, *k, *v, *shift_k, *ssm_k, *ssm_D, *wqkv, *wo, *gate_w;
  __nv_bfloat16* out;
  uint32_t zero;
};

constexpr int SPIN_LIMIT = 1 << 17;

__device__ __forceinline__ void mbar_init(uint32_t bar, uint32_t count) {
  asm volatile("mbarrier.init.shared::cta.b64 [%0], %1;" ::"r"(bar), "r"(count) : "memory");
}
__device__ __forceinline__ void mbar_expect_tx(uint32_t bar, uint32_t bytes) {
  asm volatile("mbarrier.arrive.expect_tx.shared::cta.b64 _, [%0], %1;" ::"r"(bar), "r"(bytes) : "memory");
}
__device__ __forceinline__ void mbar_arrive(uint32_t bar) {
  asm volatile("mbarrier.arrive.shared::cta.b64 _, [%0];" ::"r"(bar) : "memory");
}
__device__ __forceinline__ void mbar_wait(uint32_t bar, uint32_t parity) {
  uint32_t ok;
  int spins = 0;
  do {
      asm volatile("{\n.reg .pred p;\nmbarrier.try_wait.parity.shared::cta.b64 p, [%1], %2;\nselp.b32 %0, 1, 0, p;\n}"
                   : "=r"(ok) : "r"(bar), "r"(parity) : "memory");
    if (++spins > SPIN_LIMIT) break;
  } while (!ok);
}
__device__ __forceinline__ unsigned flag_read(const unsigned* p) {
  unsigned v;
  asm volatile("ld.relaxed.gpu.global.u32 %0, [%1];" : "=r"(v) : "l"(p) : "memory");
  return v;
}
__device__ __forceinline__ void flag_poll(const unsigned* p, unsigned target) {
  unsigned v;
  int spins = 0;
  do {
    asm volatile("ld.relaxed.gpu.global.u32 %0, [%1];" : "=r"(v) : "l"(p) : "memory");
    if (++spins > SPIN_LIMIT) break;
  } while ((int)(v - target) < 0);
}
__device__ __forceinline__ void flag_wait(const unsigned* p, unsigned target) {
  flag_poll(p, target);
}
__device__ __forceinline__ void flag_signal(unsigned* p, int n, int lane) {
  if (lane == 0) asm volatile("fence.release.gpu;" ::: "memory");
  __syncwarp();
  if (lane < n) asm volatile("red.relaxed.gpu.global.add.u32 [%0], 1;" ::"l"(p + 32 * lane) : "memory");
}
__device__ __forceinline__ void flag_bump(unsigned* p) {
  asm volatile("red.relaxed.gpu.global.add.u32 [%0], 1;" ::"l"(p) : "memory");
}
__device__ __forceinline__ void fence_async_smem() { asm volatile("fence.proxy.async.shared::cta;" ::: "memory"); }
__device__ __forceinline__ void wg_sync(int id) { asm volatile("bar.sync %0, 128;" ::"r"(id) : "memory"); }

__device__ __forceinline__ void tma_2d(uint32_t dst, const CUtensorMap* tm, int c0, int c1, uint32_t bar) {
  asm volatile("cp.async.bulk.tensor.2d.shared::cluster.global.mbarrier::complete_tx::bytes [%0], [%1, {%3, %4}], [%2];"
               ::"r"(dst), "l"(tm), "r"(bar), "r"(c0), "r"(c1) : "memory");
}
__device__ __forceinline__ void tma_3d(uint32_t dst, const CUtensorMap* tm, int c0, int c1, int c2, uint32_t bar) {
  asm volatile("cp.async.bulk.tensor.3d.shared::cluster.global.mbarrier::complete_tx::bytes [%0], [%1, {%3, %4, %5}], [%2];"
               ::"r"(dst), "l"(tm), "r"(bar), "r"(c0), "r"(c1), "r"(c2) : "memory");
}
__device__ __forceinline__ void bulk_load(uint32_t dst, const void* src, uint32_t bytes, uint32_t bar) {
  asm volatile("cp.async.bulk.shared::cluster.global.mbarrier::complete_tx::bytes [%0], [%1], %2, [%3];"
               ::"r"(dst), "l"(src), "r"(bytes), "r"(bar) : "memory");
}
__device__ __forceinline__ void bulk_store(void* dst, uint32_t src, uint32_t bytes) {
  asm volatile("cp.async.bulk.global.shared::cta.bulk_group [%0], [%1], %2;" ::"l"(dst), "r"(src), "r"(bytes) : "memory");
}
__device__ __forceinline__ void bulk_wait_read() {
  asm volatile("cp.async.bulk.commit_group;\ncp.async.bulk.wait_group.read 0;" ::: "memory");
}

__device__ __forceinline__ void publish(void* dst, uint32_t src, uint32_t bytes) {
  bulk_store(dst, src, bytes);
  bulk_wait_read();
}

__device__ __forceinline__ void wg_fence() { asm volatile("wgmma.fence.sync.aligned;" ::: "memory"); }
__device__ __forceinline__ void wg_commit() { asm volatile("wgmma.commit_group.sync.aligned;" ::: "memory"); }
template <int N> __device__ __forceinline__ void wg_wait() { asm volatile("wgmma.wait_group.sync.aligned %0;" ::"n"(N) : "memory"); }
__device__ __forceinline__ uint32_t desc_lo(uint32_t addr, uint32_t lbo) { return ((addr & 0x3FFFF) >> 4) | ((lbo >> 4) << 16); }
constexpr uint32_t desc_hi(uint32_t sbo, uint32_t swz) { return (sbo >> 4) | (swz << 30); }
constexpr uint32_t HI_SW128 = desc_hi(1024, 1), HI_SW64 = desc_hi(512, 2), HI_SW32 = desc_hi(256, 3), HI_NONE = desc_hi(128, 0);
template <int N> __device__ __forceinline__ void pin(float* d) {
#pragma unroll
  for (int i = 0; i < N; i++) asm volatile("" : "+f"(d[i])::"memory");
}

__device__ __forceinline__ uint32_t lds32(uint32_t a) {
  uint32_t v;
  asm volatile("ld.volatile.shared.u32 %0, [%1];" : "=r"(v) : "r"(a) : "memory");
  return v;
}
__device__ __forceinline__ uint2 ldg64(const void* a) {
  uint2 v;
  asm volatile("ld.global.nc.v2.u32 {%0, %1}, [%2];" : "=r"(v.x), "=r"(v.y) : "l"(a) : "memory");
  return v;
}
__device__ __forceinline__ void ldsm4(uint32_t* r, uint32_t a) {
  asm volatile("ldmatrix.sync.aligned.m8n8.x4.shared.b16 {%0, %1, %2, %3}, [%4];"
               : "=r"(r[0]), "=r"(r[1]), "=r"(r[2]), "=r"(r[3]) : "r"(a) : "memory");
}
__device__ __forceinline__ void ldsm4t(uint32_t* r, uint32_t a) {
  asm volatile("ldmatrix.sync.aligned.m8n8.x4.trans.shared.b16 {%0, %1, %2, %3}, [%4];"
               : "=r"(r[0]), "=r"(r[1]), "=r"(r[2]), "=r"(r[3]) : "r"(a) : "memory");
}
__device__ __forceinline__ uint2 lds64(uint32_t a) {
  uint2 v;
  asm volatile("ld.shared.v2.u32 {%0, %1}, [%2];" : "=r"(v.x), "=r"(v.y) : "r"(a) : "memory");
  return v;
}
__device__ __forceinline__ uint4 lds128(uint32_t a) {
  uint4 v;
  asm volatile("ld.shared.v4.u32 {%0, %1, %2, %3}, [%4];" : "=r"(v.x), "=r"(v.y), "=r"(v.z), "=r"(v.w) : "r"(a) : "memory");
  return v;
}
__device__ __forceinline__ void sts128(uint32_t a, uint32_t x, uint32_t y, uint32_t z, uint32_t w) {
  asm volatile("st.shared.v4.u32 [%0], {%1, %2, %3, %4};" ::"r"(a), "r"(x), "r"(y), "r"(z), "r"(w) : "memory");
}
__device__ __forceinline__ void stsm4(uint32_t a, const uint32_t* r) {
  asm volatile("stmatrix.sync.aligned.m8n8.x4.shared.b16 [%0], {%1, %2, %3, %4};" ::"r"(a), "r"(r[0]), "r"(r[1]), "r"(r[2]), "r"(r[3]) : "memory");
}
__device__ __forceinline__ uint32_t pack2(float lo, float hi) {
  uint32_t r;
  asm("cvt.rn.bf16x2.f32 %0, %1, %2;" : "=r"(r) : "f"(hi), "f"(lo));
  return r;
}
__device__ __forceinline__ uint32_t movm(uint32_t a) {
  uint32_t d;
  asm volatile("movmatrix.sync.aligned.m8n8.trans.b16 %0, %1;" : "=r"(d) : "r"(a));
  return d;
}
__device__ __forceinline__ uint32_t bmul(uint32_t a, uint32_t b) {
  uint32_t d;
  asm("mul.rn.bf16x2 %0, %1, %2;" : "=r"(d) : "r"(a), "r"(b));
  return d;
}
__device__ __forceinline__ uint32_t badd(uint32_t a, uint32_t b) {
  uint32_t d;
  asm("add.rn.bf16x2 %0, %1, %2;" : "=r"(d) : "r"(a), "r"(b));
  return d;
}
__device__ __forceinline__ uint32_t bfma(uint32_t a, uint32_t b, uint32_t c) {
  uint32_t d;
  asm("fma.rn.bf16x2 %0, %1, %2, %3;" : "=r"(d) : "r"(a), "r"(b), "r"(c));
  return d;
}
__device__ __forceinline__ float bf_lo(uint32_t x) { return __uint_as_float(x << 16); }
__device__ __forceinline__ float bf_hi(uint32_t x) { return __uint_as_float(x & 0xFFFF0000u); }
__device__ __forceinline__ float ex2(float x) {
  float y;
  asm("ex2.approx.ftz.f32 %0, %1;" : "=f"(y) : "f"(x));
  return y;
}
__device__ __forceinline__ float rcp(float x) {
  float y;
  asm("rcp.approx.ftz.f32 %0, %1;" : "=f"(y) : "f"(x));
  return y;
}
__device__ __forceinline__ void mma16816(float* d, uint32_t a0, uint32_t a1, uint32_t a2, uint32_t a3, uint32_t b0, uint32_t b1) {
  asm volatile("mma.sync.aligned.m16n8k16.row.col.f32.bf16.bf16.f32 {%0, %1, %2, %3}, {%4, %5, %6, %7}, {%8, %9}, {%0, %1, %2, %3};"
               : "+f"(d[0]), "+f"(d[1]), "+f"(d[2]), "+f"(d[3])
               : "r"(a0), "r"(a1), "r"(a2), "r"(a3), "r"(b0), "r"(b1));
}
__device__ __forceinline__ void mma1688(float* d, uint32_t a0, uint32_t a1, uint32_t b0) {
  asm volatile("mma.sync.aligned.m16n8k8.row.col.f32.bf16.bf16.f32 {%0, %1, %2, %3}, {%4, %5}, {%6}, {%0, %1, %2, %3};"
               : "+f"(d[0]), "+f"(d[1]), "+f"(d[2]), "+f"(d[3])
               : "r"(a0), "r"(a1), "r"(b0));
}

template <int N> struct WgRS;
template <int N> struct WgSST;
template <> struct WgRS<32> {
  template <uint32_t HB>
  static __device__ __forceinline__ void mma(float* d, const uint32_t* a, uint32_t db) {
    asm volatile("{\n.reg .pred p;\n.reg .b64 db;\nsetp.ne.b32 p, %22, 0;\n"
      "mov.b64 db, {%20, %21};\n"
      "wgmma.mma_async.sync.aligned.m64n32k16.f32.bf16.bf16 {"
      "%0, %1, %2, %3, %4, %5, %6, %7, %8, %9, %10, %11, %12, %13, %14, %15"
      "}, {%16, %17, %18, %19}, db, p, 1, 1, 1;\n}\n"
      : "+f"(d[0]), "+f"(d[1]), "+f"(d[2]), "+f"(d[3]), "+f"(d[4]), "+f"(d[5]), "+f"(d[6]), "+f"(d[7]),
        "+f"(d[8]), "+f"(d[9]), "+f"(d[10]), "+f"(d[11]), "+f"(d[12]), "+f"(d[13]), "+f"(d[14]), "+f"(d[15])
      : "r"(a[0]), "r"(a[1]), "r"(a[2]), "r"(a[3]), "r"(db), "n"(HB), "n"(1));
  }
  template <uint32_t HB>
  static __device__ __forceinline__ void set(float* d, const uint32_t* a, uint32_t db) {
    asm volatile("{\n.reg .pred p;\n.reg .b64 db;\nsetp.ne.b32 p, %22, 0;\n"
      "mov.b64 db, {%20, %21};\n"
      "wgmma.mma_async.sync.aligned.m64n32k16.f32.bf16.bf16 {"
      "%0, %1, %2, %3, %4, %5, %6, %7, %8, %9, %10, %11, %12, %13, %14, %15"
      "}, {%16, %17, %18, %19}, db, p, 1, 1, 1;\n}\n"
      : "=f"(d[0]), "=f"(d[1]), "=f"(d[2]), "=f"(d[3]), "=f"(d[4]), "=f"(d[5]), "=f"(d[6]), "=f"(d[7]),
        "=f"(d[8]), "=f"(d[9]), "=f"(d[10]), "=f"(d[11]), "=f"(d[12]), "=f"(d[13]), "=f"(d[14]), "=f"(d[15])
      : "r"(a[0]), "r"(a[1]), "r"(a[2]), "r"(a[3]), "r"(db), "n"(HB), "n"(0));
  }
};
template <> struct WgRS<64> {
  template <uint32_t HB>
  static __device__ __forceinline__ void mma(float* d, const uint32_t* a, uint32_t db) {
    asm volatile("{\n.reg .pred p;\n.reg .b64 db;\nsetp.ne.b32 p, %38, 0;\n"
      "mov.b64 db, {%36, %37};\n"
      "wgmma.mma_async.sync.aligned.m64n64k16.f32.bf16.bf16 {"
      "%0, %1, %2, %3, %4, %5, %6, %7, %8, %9, %10, %11, %12, %13, %14, %15, "
      "%16, %17, %18, %19, %20, %21, %22, %23, %24, %25, %26, %27, %28, %29, %30, %31"
      "}, {%32, %33, %34, %35}, db, p, 1, 1, 1;\n}\n"
      : "+f"(d[0]), "+f"(d[1]), "+f"(d[2]), "+f"(d[3]), "+f"(d[4]), "+f"(d[5]), "+f"(d[6]), "+f"(d[7]),
        "+f"(d[8]), "+f"(d[9]), "+f"(d[10]), "+f"(d[11]), "+f"(d[12]), "+f"(d[13]), "+f"(d[14]), "+f"(d[15]),
        "+f"(d[16]), "+f"(d[17]), "+f"(d[18]), "+f"(d[19]), "+f"(d[20]), "+f"(d[21]), "+f"(d[22]), "+f"(d[23]),
        "+f"(d[24]), "+f"(d[25]), "+f"(d[26]), "+f"(d[27]), "+f"(d[28]), "+f"(d[29]), "+f"(d[30]), "+f"(d[31])
      : "r"(a[0]), "r"(a[1]), "r"(a[2]), "r"(a[3]), "r"(db), "n"(HB), "n"(1));
  }
  template <uint32_t HB>
  static __device__ __forceinline__ void set(float* d, const uint32_t* a, uint32_t db) {
    asm volatile("{\n.reg .pred p;\n.reg .b64 db;\nsetp.ne.b32 p, %38, 0;\n"
      "mov.b64 db, {%36, %37};\n"
      "wgmma.mma_async.sync.aligned.m64n64k16.f32.bf16.bf16 {"
      "%0, %1, %2, %3, %4, %5, %6, %7, %8, %9, %10, %11, %12, %13, %14, %15, "
      "%16, %17, %18, %19, %20, %21, %22, %23, %24, %25, %26, %27, %28, %29, %30, %31"
      "}, {%32, %33, %34, %35}, db, p, 1, 1, 1;\n}\n"
      : "=f"(d[0]), "=f"(d[1]), "=f"(d[2]), "=f"(d[3]), "=f"(d[4]), "=f"(d[5]), "=f"(d[6]), "=f"(d[7]),
        "=f"(d[8]), "=f"(d[9]), "=f"(d[10]), "=f"(d[11]), "=f"(d[12]), "=f"(d[13]), "=f"(d[14]), "=f"(d[15]),
        "=f"(d[16]), "=f"(d[17]), "=f"(d[18]), "=f"(d[19]), "=f"(d[20]), "=f"(d[21]), "=f"(d[22]), "=f"(d[23]),
        "=f"(d[24]), "=f"(d[25]), "=f"(d[26]), "=f"(d[27]), "=f"(d[28]), "=f"(d[29]), "=f"(d[30]), "=f"(d[31])
      : "r"(a[0]), "r"(a[1]), "r"(a[2]), "r"(a[3]), "r"(db), "n"(HB), "n"(0));
  }
};
template <> struct WgSST<48> {
  template <uint32_t HA, uint32_t HB>
  static __device__ __forceinline__ void mma(float* d, uint32_t da, uint32_t db, int sc) {
    asm volatile("{\n.reg .pred p;\n.reg .b64 da, db;\nsetp.ne.b32 p, %28, 0;\n"
      "mov.b64 da, {%24, %25};\nmov.b64 db, {%26, %27};\n"
      "wgmma.mma_async.sync.aligned.m64n48k16.f32.bf16.bf16 {"
      "%0, %1, %2, %3, %4, %5, %6, %7, %8, %9, %10, %11, %12, %13, %14, %15, "
      "%16, %17, %18, %19, %20, %21, %22, %23"
      "}, da, db, p, 1, 1, 0, 1;\n}\n"
      : "+f"(d[0]), "+f"(d[1]), "+f"(d[2]), "+f"(d[3]), "+f"(d[4]), "+f"(d[5]), "+f"(d[6]), "+f"(d[7]),
        "+f"(d[8]), "+f"(d[9]), "+f"(d[10]), "+f"(d[11]), "+f"(d[12]), "+f"(d[13]), "+f"(d[14]), "+f"(d[15]),
        "+f"(d[16]), "+f"(d[17]), "+f"(d[18]), "+f"(d[19]), "+f"(d[20]), "+f"(d[21]), "+f"(d[22]), "+f"(d[23])
      : "r"(da), "n"(HA), "r"(db), "n"(HB), "r"(sc));
  }
};
template <> struct WgSST<80> {
  template <uint32_t HA, uint32_t HB>
  static __device__ __forceinline__ void mma(float* d, uint32_t da, uint32_t db, int sc) {
    asm volatile("{\n.reg .pred p;\n.reg .b64 da, db;\nsetp.ne.b32 p, %44, 0;\n"
      "mov.b64 da, {%40, %41};\nmov.b64 db, {%42, %43};\n"
      "wgmma.mma_async.sync.aligned.m64n80k16.f32.bf16.bf16 {"
      "%0, %1, %2, %3, %4, %5, %6, %7, %8, %9, %10, %11, %12, %13, %14, %15, "
      "%16, %17, %18, %19, %20, %21, %22, %23, %24, %25, %26, %27, %28, %29, %30, %31, "
      "%32, %33, %34, %35, %36, %37, %38, %39"
      "}, da, db, p, 1, 1, 0, 1;\n}\n"
      : "+f"(d[0]), "+f"(d[1]), "+f"(d[2]), "+f"(d[3]), "+f"(d[4]), "+f"(d[5]), "+f"(d[6]), "+f"(d[7]),
        "+f"(d[8]), "+f"(d[9]), "+f"(d[10]), "+f"(d[11]), "+f"(d[12]), "+f"(d[13]), "+f"(d[14]), "+f"(d[15]),
        "+f"(d[16]), "+f"(d[17]), "+f"(d[18]), "+f"(d[19]), "+f"(d[20]), "+f"(d[21]), "+f"(d[22]), "+f"(d[23]),
        "+f"(d[24]), "+f"(d[25]), "+f"(d[26]), "+f"(d[27]), "+f"(d[28]), "+f"(d[29]), "+f"(d[30]), "+f"(d[31]),
        "+f"(d[32]), "+f"(d[33]), "+f"(d[34]), "+f"(d[35]), "+f"(d[36]), "+f"(d[37]), "+f"(d[38]), "+f"(d[39])
      : "r"(da), "n"(HA), "r"(db), "n"(HB), "r"(sc));
  }
};
template <> struct WgSST<192> {
  template <uint32_t HA, uint32_t HB>
  static __device__ __forceinline__ void mma(float* d, uint32_t da, uint32_t db, int sc) {
    asm volatile("{\n.reg .pred p;\n.reg .b64 da, db;\nsetp.ne.b32 p, %100, 0;\n"
      "mov.b64 da, {%96, %97};\nmov.b64 db, {%98, %99};\n"
      "wgmma.mma_async.sync.aligned.m64n192k16.f32.bf16.bf16 {"
      "%0, %1, %2, %3, %4, %5, %6, %7, %8, %9, %10, %11, %12, %13, %14, %15, "
      "%16, %17, %18, %19, %20, %21, %22, %23, %24, %25, %26, %27, %28, %29, %30, %31, "
      "%32, %33, %34, %35, %36, %37, %38, %39, %40, %41, %42, %43, %44, %45, %46, %47, "
      "%48, %49, %50, %51, %52, %53, %54, %55, %56, %57, %58, %59, %60, %61, %62, %63, "
      "%64, %65, %66, %67, %68, %69, %70, %71, %72, %73, %74, %75, %76, %77, %78, %79, "
      "%80, %81, %82, %83, %84, %85, %86, %87, %88, %89, %90, %91, %92, %93, %94, %95"
      "}, da, db, p, 1, 1, 0, 1;\n}\n"
      : "+f"(d[0]), "+f"(d[1]), "+f"(d[2]), "+f"(d[3]), "+f"(d[4]), "+f"(d[5]), "+f"(d[6]), "+f"(d[7]),
        "+f"(d[8]), "+f"(d[9]), "+f"(d[10]), "+f"(d[11]), "+f"(d[12]), "+f"(d[13]), "+f"(d[14]), "+f"(d[15]),
        "+f"(d[16]), "+f"(d[17]), "+f"(d[18]), "+f"(d[19]), "+f"(d[20]), "+f"(d[21]), "+f"(d[22]), "+f"(d[23]),
        "+f"(d[24]), "+f"(d[25]), "+f"(d[26]), "+f"(d[27]), "+f"(d[28]), "+f"(d[29]), "+f"(d[30]), "+f"(d[31]),
        "+f"(d[32]), "+f"(d[33]), "+f"(d[34]), "+f"(d[35]), "+f"(d[36]), "+f"(d[37]), "+f"(d[38]), "+f"(d[39]),
        "+f"(d[40]), "+f"(d[41]), "+f"(d[42]), "+f"(d[43]), "+f"(d[44]), "+f"(d[45]), "+f"(d[46]), "+f"(d[47]),
        "+f"(d[48]), "+f"(d[49]), "+f"(d[50]), "+f"(d[51]), "+f"(d[52]), "+f"(d[53]), "+f"(d[54]), "+f"(d[55]),
        "+f"(d[56]), "+f"(d[57]), "+f"(d[58]), "+f"(d[59]), "+f"(d[60]), "+f"(d[61]), "+f"(d[62]), "+f"(d[63]),
        "+f"(d[64]), "+f"(d[65]), "+f"(d[66]), "+f"(d[67]), "+f"(d[68]), "+f"(d[69]), "+f"(d[70]), "+f"(d[71]),
        "+f"(d[72]), "+f"(d[73]), "+f"(d[74]), "+f"(d[75]), "+f"(d[76]), "+f"(d[77]), "+f"(d[78]), "+f"(d[79]),
        "+f"(d[80]), "+f"(d[81]), "+f"(d[82]), "+f"(d[83]), "+f"(d[84]), "+f"(d[85]), "+f"(d[86]), "+f"(d[87]),
        "+f"(d[88]), "+f"(d[89]), "+f"(d[90]), "+f"(d[91]), "+f"(d[92]), "+f"(d[93]), "+f"(d[94]), "+f"(d[95])
      : "r"(da), "n"(HA), "r"(db), "n"(HB), "r"(sc));
  }
};

struct FftConst {
  uint32_t f[2][4], fi[4][4];
  uint32_t ta[2][2], tb[2][2];
};
__device__ __forceinline__ void cis(int m, float scale, float& c, float& s) {
  const float a = (float)m * (-6.283185307179586f * scale);
  c = __cosf(a);
  s = __sinf(a);
}
__device__ __forceinline__ void fft_tables(uint32_t (&v)[12], int tw) {
  const int row = tw >> 2, ch = tw & 3;
#pragma unroll
  for (int i = 0; i < 4; i++) {
    float c[2], s[2], x[2];
#pragma unroll
    for (int e = 0; e < 2; e++) {
      cis((((32 * (8 * ch + 2 * i + e) + 15) * (4 * row - 63) + 2048) & 4095) - 2048, 1.f / 4096, c[e], s[e]);
      float gc, gs;
      cis((((row & 15) * (8 * (ch & 1) + 2 * i + e) + 8) & 15) - 8, 1.f / 16, gc, gs);
      x[e] = (row >> 4) == (ch >> 1) ? gc : (ch >> 1) ? gs : -gs;
    }
    v[i] = pack2(c[0] * 0.125f, c[1] * 0.125f);
    v[4 + i] = pack2(s[0] * 0.125f, s[1] * 0.125f);
    v[8 + i] = pack2(x[0], x[1]);
  }
#pragma unroll
  for (int i = 0; i < 12; i++) asm volatile("" : "+r"(v[i]));
}
__device__ __forceinline__ void fft_tables_store(const uint32_t (&v)[12], uint32_t sb, int tw) {
  const int row = tw >> 2;
  const uint32_t x = ((tw ^ (row >> 1)) & 3) << 4, a = sb + OFF_FT + (16 * (row >> 3) + (row & 7)) * 64 + x;
  sts128(a, v[0], v[1], v[2], v[3]);
  sts128(a + 512, v[4], v[5], v[6], v[7]);
  sts128(sb + OFF_GT + row * 64 + x, v[8], v[9], v[10], v[11]);
}
__device__ __forceinline__ void fft_twiddles(uint32_t (&v)[2], int tw) {
  float a[2], s[2];
#pragma unroll
  for (int i = 0; i < 2; i++) {
    float c;
    cis((2 * (2 * (tw & 3) + i) - 15) * (4 * (tw >> 2) - 63), 1.f / 4096, c, s[i]);
    a[i] = __fdividef(-s[i], 1.f + c);
  }
  v[0] = pack2(a[0], a[1]);
  v[1] = pack2(s[0], s[1]);
  asm volatile("" : "+r"(v[0]), "+r"(v[1]));
}
__device__ __forceinline__ void fft_matrices(FftConst& k, uint32_t sb, int w, int lane) {
  const uint32_t x = (lane >> 1) & 3;
  const uint2 t0 = lds64(sb + OFF_TT + 256 * w + 8 * lane), t1 = lds64(sb + OFF_TT + 256 * w + 8 * (lane ^ 3));
  k.ta[0][0] = t0.x;
  k.tb[0][0] = t0.y;
  k.ta[1][1] = __byte_perm(t1.x, 0, 0x1032);
  k.tb[1][1] = __byte_perm(t1.y, 0, 0x1032);
#pragma unroll
  for (int j = 0; j < 2; j++) {
    k.ta[1 - j][j] = k.ta[j][j] ^ 0x80008000u;
    k.tb[1 - j][j] = k.tb[j][j] ^ 0x80008000u;
    asm volatile("" : "+r"(k.ta[0][j]), "+r"(k.tb[0][j]), "+r"(k.ta[1][j]), "+r"(k.tb[1][j]));
  }
#pragma unroll
  for (int i = 0; i < 2; i++) {
    ldsm4(k.f[i], sb + OFF_FT + (16 * w + (lane & 15)) * 64 + (((2 * i + (lane >> 4)) ^ x) << 4));
    ldsm4t(k.fi[i], sb + OFF_FT + (32 * i + lane) * 64 + ((w ^ x) << 4));
#pragma unroll
    for (int j = 0; j < 4; j++) {
      k.fi[2 + i][j] = (j & 1) ? k.fi[i][j - 1] ^ 0x80008000u : k.fi[i][j + 1];
      asm volatile("" : "+r"(k.fi[2 + i][j]));
    }
  }
}
__device__ __forceinline__ void rot(uint32_t& x, uint32_t& y, uint32_t a, uint32_t b) {
  x = bfma(a, y, x);
  y = bfma(b, x, y);
  x = bfma(a, y, x);
}
__device__ __forceinline__ void twiddle_fwd(uint32_t (&a)[4][4], float* d, const FftConst& k) {
#pragma unroll
  for (int q = 0; q < 4; q++)
#pragma unroll
    for (int j = 0; j < 2; j++) {
      const float* x = d + 8 * q + 4 * j;
      uint32_t re = pack2(x[0], x[1]), im = pack2(x[2], x[3]);
      rot(re, im, k.ta[0][j], k.tb[0][j]);
      a[q & 2][2 * j + (q & 1)] = re;
      a[(q & 2) + 1][2 * j + (q & 1)] = im;
    }
}
__device__ __forceinline__ void g_step(float* d, const uint32_t (&a)[4][4], uint32_t dre, uint32_t dim) {
  WgRS<32>::set<HI_SW64>(d, a[0], dre);
  WgRS<32>::set<HI_SW64>(d + 16, a[2], dre);
  WgRS<32>::mma<HI_SW64>(d, a[1], dim);
  WgRS<32>::mma<HI_SW64>(d + 16, a[3], dim);
  wg_commit();
}

__device__ __forceinline__ void products(uint32_t (&a)[4][4], const float* H, const float* U, int p) {
#pragma unroll
  for (int j = 0; j < 2; j++)
#pragma unroll
    for (int m = 2 * p; m < 2 * p + 2; m++) {
      float pr[2], pi[2];
#pragma unroll
      for (int x = 0; x < 2; x++)
#pragma unroll
        for (int q = 0; q <= m; q++) {
          const int ih = 16 * (q >> 1) + 2 * (q & 1) + 4 * j + x, iu = 16 * ((m - q) >> 1) + 2 * ((m - q) & 1) + 4 * j + x;
          pr[x] = q ? fmaf(H[ih], U[iu], pr[x]) : H[ih] * U[iu];
          pi[x] = q ? fmaf(H[ih], U[iu + 8], pi[x]) : H[ih] * U[iu + 8];
          pr[x] = fmaf(-H[ih + 8], U[iu + 8], pr[x]);
          pi[x] = fmaf(H[ih + 8], U[iu], pi[x]);
        }
      a[m & 2][2 * j + (m & 1)] = pack2(pr[0], pr[1]);
      a[(m & 2) + 1][2 * j + (m & 1)] = pack2(pi[0], pi[1]);
    }
}

__device__ __forceinline__ void f_step(float* d, const FftConst& k, uint32_t db) {
  WgRS<64>::set<HI_SW32>(d, k.f[0], db);
  WgRS<64>::mma<HI_SW32>(d, k.f[1], db + 32);
  wg_commit();
}
__device__ __forceinline__ uint32_t desc_h(uint32_t sb, uint32_t tasks) { return desc_lo(sb + off_ch((tasks & 7) - 1) + U_BYTES, 1024); }
__device__ __forceinline__ void last_step(float* d, const FftConst& k, uint32_t dz) {
  wg_fence();
  WgRS<64>::set<HI_SW128>(d, k.fi[0], dz);
#pragma unroll
  for (int ks = 1; ks < 4; ks++) WgRS<64>::mma<HI_SW128>(d, k.fi[ks], dz + 128 * ks);
  wg_commit();
}
__device__ __forceinline__ void conv_channel(const FftConst& k, uint32_t (&a)[4][4], uint32_t sb, int c, uint32_t next, int wg, int w, int lane) {
  const uint32_t cb = sb + off_ch(c), bars = sb + OFF_BAR;
  const uint32_t du = desc_lo(cb, 1024), dg = desc_lo(sb + OFF_GT, 16), dz = desc_lo(cb + U_BYTES, 16);
  float U[32], H[32];
  uint32_t e[4][4];
  const float dv = __uint_as_float(lds32(sb + OFF_D + 4 * c));
  mbar_wait(bars + 8 * (B_U + (c < 3 ? c : 3)), 0);
  TSM(w == 0 && c < 3, 7 + wg);
  wg_fence();
  f_step(U, k, du);
  g_step(H, a, dg, dg + 64);
  wg_wait<1>();
  pin<32>(U);
  twiddle_fwd(e, U, k);
  wg_fence();
  g_step(U, e, dg, dg + 64);
  wg_wait<0>();
  pin<32>(U);
  pin<32>(H);
#pragma unroll
  for (int j = 0; j < 4; j++) H[4 * (j >> 1) + (j & 1)] += dv;
  float V[32];
#pragma unroll
  for (int p = 0; p < 2; p++) {
    products(a, H, U, p);
    wg_fence();
    WgRS<32>::set<HI_SW64>(V + 16 * p, a[2 * p], dg + 64);
    WgRS<32>::mma<HI_SW64>(V + 16 * p, a[2 * p + 1], dg);
    wg_commit();
  }
  const uint32_t za = cb + U_BYTES + (8 * w + (lane & 7)) * 128 + (((lane >> 3) ^ (lane & 7)) << 4);
  const uint32_t ya = cb + (lane >> 4) * 1024 + (8 * w + (lane & 7)) * 32 + ((((lane >> 3) ^ (lane >> 2)) & 1) << 4);
  wg_sync(1 + wg);
#pragma unroll
  for (int p = 0; p < 2; p++) {
    if (p == 0) wg_wait<1>();
    else wg_wait<0>();
    pin<16>(V + 16 * p);
#pragma unroll
    for (int i = 0; i < 4; i++) {
      const int j = i & 1;
      const float* x = V + 16 * p + 4 * j + (i & 2);
      e[p][i] = pack2(x[8], x[9]);
      e[2 + p][i] = pack2(x[0], x[1]);
      rot(e[p][i], e[2 + p][i], k.ta[1][j], k.tb[1][j]);
    }
    stsm4(za ^ (64 * p), e[p]);
    stsm4((za ^ (64 * p)) + 4096, e[2 + p]);
  }
  if (next) {
    wg_fence();
    f_step(U, k, desc_h(sb, next));
    fence_async_smem();
    wg_sync(1 + wg);
    last_step(H, k, dz);
    wg_wait<1>();
    pin<32>(U);
    twiddle_fwd(a, U, k);
    wg_wait<0>();
  } else {
    fence_async_smem();
    wg_sync(1 + wg);
    last_step(H, k, dz);
    wg_wait<0>();
  }
  pin<32>(H);
  if (lane == 0) mbar_arrive(bars + 8 * B_CVD);
  TSIF(w == 0, 88 + c);
#pragma unroll
  for (int j = 0; j < 8; j++)
    e[j >> 2][j & 3] = j < 2 ? pack2(H[4 * j], H[4 * j + 1]) : pack2(H[4 * j] + H[4 * j - 6], H[4 * j + 1] + H[4 * j - 5]);
  stsm4(ya, e[0]);
  stsm4(ya + 2048, e[1]);
  fence_async_smem();
  __syncwarp();
}

__device__ __forceinline__ void prep_slab(uint4* res, const uint2* sw, uint32_t sb, int slab, int w, int lane) {
  const int t = lane & 3, tp = (lane & 7) >> 1, pos = 8 * tp + 2 * (((lane >> 3) + tp) & 3) + (lane & 1);
  const uint32_t base = sb + OFF_KVS + slab * KVS_BYTES + pos * 128;
  uint32_t kk[2][4][4], vv[2][4];
  mbar_wait(sb + OFF_BAR + 8 * (B_KV + slab), 0);
#pragma unroll
  for (int h = 0; h < 2; h++) {
#pragma unroll
    for (int j = 0; j < 4; j++) {
      const uint32_t a = base + 128 * j;
      ldsm4t(kk[h][j], a + (((w + 4 * h) ^ ((a >> 7) & 7)) << 4));
    }
    const uint32_t a = base + KVS_V;
    ldsm4t(vv[h], a + (((w + 4 * h) ^ ((a >> 7) & 7)) << 4));
  }
#pragma unroll
  for (int h = 0; h < 2; h++) {
    uint32_t (&k)[4][4] = kk[h];
    uint32_t (&v)[4] = vv[h];
    const uint32_t w0 = __byte_perm(sw[h].x, 0, 0x1010), w1 = __byte_perm(sw[h].x, 0, 0x3232);
    const uint32_t w2 = __byte_perm(sw[h].y, 0, 0x1010), w3 = __byte_perm(sw[h].y, 0, 0x3232);
#pragma unroll
    for (int m = 0; m < 4; m++)
      v[m] = bmul(badd(badd(badd(bmul(k[0][m], w3), bmul(k[1][m], w2)), bmul(k[2][m], w1)), bmul(k[3][m], w0)), v[m]);
    uint32_t a[4];
#pragma unroll
    for (int m = 0; m < 4; m++) a[m] = (t & 1) ? v[(m + 3) & 3] : v[m];
    res[h] = (t & 2) ? make_uint4(a[2], a[3], a[0], a[1]) : make_uint4(a[0], a[1], a[2], a[3]);
  }
}

__device__ __forceinline__ void prep_gate(const Params& p, uint32_t sb, int b, int w, int lane) {
  uint2 gw[5], x[4][5];
#pragma unroll
  for (int j = 0; j < 5; j++) gw[j] = ldg64(reinterpret_cast<const uint2*>(p.gate_w) + lane + 32 * j);
#pragma unroll
  for (int i = 0; i < 4; i++)
#pragma unroll
    for (int j = 0; j < 5; j++)
      x[i][j] = ldg64(reinterpret_cast<const uint2*>(p.q) + (16 * b + 4 * w + i) * (DIM / 4) + lane + 32 * j);
  float s[4];
#pragma unroll
  for (int i = 0; i < 4; i++) {
    s[i] = 0.f;
#pragma unroll
    for (int j = 0; j < 5; j++) {
      const uint32_t m0 = bmul(x[i][j].x, gw[j].x), m1 = bmul(x[i][j].y, gw[j].y);
      s[i] += (bf_lo(m0) + bf_hi(m0)) + (bf_lo(m1) + bf_hi(m1));
    }
  }
  const bool h = lane & 16, q = lane & 8;
  const float a = (h ? s[2] : s[0]) + __shfl_xor_sync(0xffffffffu, h ? s[0] : s[2], 16);
  const float c = (h ? s[3] : s[1]) + __shfl_xor_sync(0xffffffffu, h ? s[1] : s[3], 16);
  float z = (q ? c : a) + __shfl_xor_sync(0xffffffffu, q ? a : c, 8);
#pragma unroll
  for (int o = 4; o > 0; o >>= 1) z += __shfl_xor_sync(0xffffffffu, z, o);
  z = bf_lo(pack2(z, 0.f));
  z = bf_lo(pack2(__fdividef(1.f, 1.f + __expf(-z)), 0.f));
  mbar_wait(sb + OFF_BAR + 8 * B_S3, 0);
  if ((lane & 7) == 0) asm volatile("st.shared.f32 [%0], %1;" ::"r"(sb + OFF_GATE + 64 * (b & 7) + 16 * w + (lane >> 1)), "f"(z) : "memory");
  fence_async_smem();
}

__device__ __forceinline__ uint32_t bmax(uint32_t a, uint32_t b) {
  uint32_t d;
  asm("max.bf16x2 %0, %1, %2;" : "=r"(d) : "r"(a), "r"(b));
  return d;
}
__device__ __forceinline__ void softmax_two(const float (&l)[2][2], uint32_t& p0, uint32_t& p1) {
  constexpr float kScale = 0.22360679774997896f, kLog2e = 1.4426950408889634f;
  const uint32_t r0 = pack2(l[0][0], l[1][0]), r1 = pack2(l[0][1], l[1][1]);
  const uint32_t x0 = pack2(bf_lo(r0) * kScale, bf_hi(r0) * kScale), x1 = pack2(bf_lo(r1) * kScale, bf_hi(r1) * kScale);
  uint32_t m = bmax(x0, x1);
  m = bmax(m, __shfl_xor_sync(0xffffffffu, m, 1));
  m = bmax(m, __shfl_xor_sync(0xffffffffu, m, 2));
  const float m0 = bf_lo(m) * kLog2e, m1 = bf_hi(m) * kLog2e;
  p0 = pack2(ex2(bf_lo(x0) * kLog2e - m0), ex2(bf_lo(x1) * kLog2e - m0));
  p1 = pack2(ex2(bf_hi(x0) * kLog2e - m1), ex2(bf_hi(x1) * kLog2e - m1));
}

__device__ __forceinline__ void halo_read(uint32_t (&kpv)[10], uint32_t (&vpv)[10], uint32_t (&tg)[7], const uint4* hp) {
#pragma unroll
  for (int j = 0; j < 7; j++) {
    uint32_t x0, x1, x2;
    asm volatile("ld.relaxed.gpu.global.v4.u32 {%0, %1, %2, %3}, [%4];"
                 : "=r"(x0), "=r"(x1), "=r"(x2), "=r"(tg[j]) : "l"(hp + 32 * j) : "memory");
    if (j < 4) kpv[3 * j] = x0; else vpv[3 * j - 10] = x0;
    if (j < 3) kpv[3 * j + 1] = x1; else vpv[3 * j - 9] = x1;
    if (j < 3) kpv[3 * j + 2] = x2; else if (j < 6) vpv[3 * j - 8] = x2;
  }
}

template <int ROT>
__device__ __forceinline__ void pack_qkv(const float* acc, uint32_t (&qlo)[10], uint32_t (&qhi)[10], uint32_t (&klo)[10],
                                         uint32_t (&khi)[10], uint32_t (&vlo)[10], uint32_t (&vhi)[10]) {
#pragma unroll
  for (int j = 0; j < 10; j++) {
    const int x = (j + ROT) % 10, tq = x < 8 ? x : 16 + x, tk = x < 8 ? 8 + x : 18 + x, tv = x < 8 ? 16 + x : 20 + x;
    khi[j] = pack2(acc[4 * tk + 2], acc[4 * tk + 3]);
    vhi[j] = movm(pack2(acc[4 * tv + 2], acc[4 * tv + 3]));
    qlo[j] = pack2(acc[4 * tq], acc[4 * tq + 1]);
    qhi[j] = pack2(acc[4 * tq + 2], acc[4 * tq + 3]);
    klo[j] = pack2(acc[4 * tk], acc[4 * tk + 1]);
    vlo[j] = pack2(acc[4 * tv], acc[4 * tv + 1]);
    asm volatile("" : "+r"(khi[j]), "+r"(qlo[j]), "+r"(qhi[j]), "+r"(klo[j]), "+r"(vlo[j]));
  }
}

template <int ROT> __device__ __forceinline__ void halo_send(const float* acc, uint4* ho, uint32_t tag) {
#pragma unroll
  for (int j = 0; j < 7; j++) {
    uint32_t x[3];
#pragma unroll
    for (int e = 0; e < 3; e++) {
      const int i = 3 * j + e, y = (i % 10 + ROT) % 10, tk = y < 8 ? 8 + y : 18 + y, tv = y < 8 ? 16 + y : 20 + y;
      x[e] = i < 10 ? pack2(acc[4 * tk + 2], acc[4 * tk + 3]) : i < 20 ? movm(pack2(acc[4 * tv + 2], acc[4 * tv + 3])) : 0u;
    }
    asm volatile("st.relaxed.gpu.global.v4.u32 [%0], {%1, %2, %3, %4};" ::"l"(ho + 32 * j), "r"(x[0]), "r"(x[1]), "r"(x[2]), "r"(tag) : "memory");
  }
}

__device__ __forceinline__ void attention(float* acc, uint32_t sb, int b, int par, int w, int lane, uint32_t tag, FftConst& fc, uint32_t (&fa)[4][4]) {
  const int g = lane >> 2, t = lane & 3;
  uint32_t klo[10], khi[10], vlo[10], vhi[10], qlo[10], qhi[10], kpv[10], vpv[10];
  if (w == 3 && b < NCTA - 8) {
    uint4* ho = g_halo + (b * 2 + par) * 224 + lane;
    if (tail_first(b & 7)) halo_send<8>(acc, ho, tag);
    else halo_send<0>(acc, ho, tag);
    TSIF(par == 0, 76);
    pin<120>(acc);
  }
  if (tail_first(b & 7)) pack_qkv<8>(acc, qlo, qhi, klo, khi, vlo, vhi);
  else pack_qkv<0>(acc, qlo, qhi, klo, khi, vlo, vhi);
  const uint32_t xa = sb + OFF_KVX + (par * 3) * 2560 + lane * 16;
  if (w < 3) {
    sts128(xa + w * 2560, khi[0], khi[1], khi[2], khi[3]);
    sts128(xa + w * 2560 + 512, khi[4], khi[5], khi[6], khi[7]);
    sts128(xa + w * 2560 + 1024, khi[8], khi[9], vhi[0], vhi[1]);
    sts128(xa + w * 2560 + 1536, vhi[2], vhi[3], vhi[4], vhi[5]);
    sts128(xa + w * 2560 + 2048, vhi[6], vhi[7], vhi[8], vhi[9]);
  }
  TSIF(par == 0 && w == 1, 64);
#pragma unroll
  for (int j = 0; j < 10; j++) vlo[j] = movm(vlo[j]);
  const bool far0 = 2 * t > g, far1 = 2 * t + 1 > g;
  const uint32_t mfar = (far0 ? 0x0000FFFFu : 0u) | (far1 ? 0xFFFF0000u : 0u);
  float slo[4][2], lg[2][2];
  uint32_t phi[4], plo[4], qml[4], qmh[4];
#pragma unroll
  for (int h = 0; h < 4; h++) {
    const int f = h == 0 ? 0 : h == 1 ? 3 : h == 2 ? 5 : 8, hf = h < 2 ? 2 : 7;
    const bool mine = (h & 1) ? t >= 2 : t < 2;
    qml[h] = mine ? qlo[hf] : 0u;
    qmh[h] = mine ? qhi[hf] : 0u;
    float a[4] = {0.f, 0.f, 0.f, 0.f}, c[4] = {0.f, 0.f, 0.f, 0.f};
    mma16816(a, qlo[f], qhi[f], qlo[f + 1], qhi[f + 1], klo[f], klo[f + 1]);
    mma16816(c, qlo[f], qhi[f], qlo[f + 1], qhi[f + 1], khi[f], khi[f + 1]);
    mma1688(a, qml[h], qmh[h], klo[hf]);
    mma1688(c, qml[h], qmh[h], khi[hf]);
    slo[h][0] = a[0];
    slo[h][1] = a[1];
    lg[h & 1][0] = far0 ? a[2] : c[2];
    lg[h & 1][1] = far1 ? a[3] : c[3];
    if (h & 1) softmax_two(lg, phi[h - 1], phi[h]);
  }
  TSIF(par == 0 && w == 1, 65);
  wg_sync(1 + par);
  TSIF(par == 0 && w == 1, 66);
  const bool nohist = (w == 0) && (b < 8);
  const uint4* hp = g_halo + ((b - 8) * 2 + par) * 224 + lane;
  uint32_t tg[7];
  if (w > 0) {
    const uint4 v0 = lds128(xa + (w - 1) * 2560), v1 = lds128(xa + (w - 1) * 2560 + 512), v2 = lds128(xa + (w - 1) * 2560 + 1024);
    const uint4 v3 = lds128(xa + (w - 1) * 2560 + 1536), v4 = lds128(xa + (w - 1) * 2560 + 2048);
    kpv[0] = v0.x; kpv[1] = v0.y; kpv[2] = v0.z; kpv[3] = v0.w; kpv[4] = v1.x; kpv[5] = v1.y; kpv[6] = v1.z; kpv[7] = v1.w;
    kpv[8] = v2.x; kpv[9] = v2.y; vpv[0] = v2.z; vpv[1] = v2.w; vpv[2] = v3.x; vpv[3] = v3.y; vpv[4] = v3.z; vpv[5] = v3.w;
    vpv[6] = v4.x; vpv[7] = v4.y; vpv[8] = v4.z; vpv[9] = v4.w;
  } else if (nohist) {
#pragma unroll
    for (int j = 0; j < 10; j++) kpv[j] = vpv[j] = 0u;
  } else {
    TSIF(par == 0, 77);
    halo_read(kpv, vpv, tg, hp);
  }
  if (w == 0 && !nohist) {
    int spins = 0;
    while (true) {
      bool ok = true;
#pragma unroll
      for (int j = 0; j < 7; j++) ok = ok && tg[j] == tag;
      if (__all_sync(0xffffffffu, ok) || ++spins > SPIN_LIMIT) break;
      halo_read(kpv, vpv, tg, hp);
    }
    TSIF(par == 0, 79);
  }
#pragma unroll
  for (int h = 0; h < 4; h++) {
    const int f = h == 0 ? 0 : h == 1 ? 3 : h == 2 ? 5 : 8, hf = h < 2 ? 2 : 7;
    float a[4] = {0.f, 0.f, 0.f, 0.f};
    mma16816(a, qlo[f], qhi[f], qlo[f + 1], qhi[f + 1], kpv[f], kpv[f + 1]);
    mma1688(a, qml[h], qmh[h], kpv[hf]);
    const float ninf = __int_as_float(0xff800000);
    lg[h & 1][0] = far0 ? (nohist ? ninf : a[0]) : slo[h][0];
    lg[h & 1][1] = far1 ? (nohist ? ninf : a[1]) : slo[h][1];
    if (h & 1) softmax_two(lg, plo[h - 1], plo[h]);
  }
  TSIF(par == 0 && w <= 1, 67 + w);
  uint32_t ov[20];
#pragma unroll
  for (int hp = 0; hp < 2; hp++) {
    if (FC_AT == 1 + hp) {
      mbar_wait(sb + OFF_BAR + 8 * B_HA, 0);
      fft_matrices(fc, sb, w, lane);
    }
    const int hf = hp ? 7 : 2;
    float sh[4] = {0.f, 0.f, 0.f, 0.f}, i0 = 0.f, i1 = 0.f;
#pragma unroll
    for (int e = 0; e < 2; e++) {
      const int h = 2 * hp + e, f = h == 0 ? 0 : h == 1 ? 3 : h == 2 ? 5 : 8;
      const uint32_t a0 = plo[h] & mfar, a2 = plo[h] & ~mfar, a3 = phi[h] & mfar, c1 = phi[h] & ~mfar;
      float sum[4] = {0.f, 0.f, 0.f, 0.f};
      mma1688(sum, plo[h], phi[h], 0x3F803F80u);
      const float r0 = rcp(sum[0]), r1 = rcp(sum[2]);
#pragma unroll
      for (int j = f; j < f + 2; j++) {
        float o[4] = {0.f, 0.f, 0.f, 0.f};
        mma16816(o, a0, 0u, a2, a3, vpv[j], vlo[j]);
        mma1688(o, 0u, c1, vhi[j]);
        ov[2 * j] = pack2(o[0] * r0, o[1] * r0);
        ov[2 * j + 1] = pack2(o[2] * r1, o[3] * r1);
      }
      const bool mine = e ? g >= 4 : g < 4;
      mma16816(sh, a0, 0u, a2, a3, mine ? vpv[hf] : 0u, mine ? vlo[hf] : 0u);
      mma1688(sh, 0u, c1, mine ? vhi[hf] : 0u);
      if (e == 0 || t >= 2) {
        i0 = r0;
        i1 = r1;
      }
    }
    ov[2 * hf] = pack2(sh[0] * i0, sh[1] * i0);
    ov[2 * hf + 1] = pack2(sh[2] * i1, sh[3] * i1);
  }
  TS(32 + 4 * par + w);
  if (FC_AT == 3) {
    mbar_wait(sb + OFF_BAR + 8 * B_HA, 0);
    fft_matrices(fc, sb, w, lane);
  }
  float X[32];
  wg_fence();
  f_step(X, fc, desc_h(sb, par ? TASK1 : TASK0));
  mbar_wait(sb + OFF_BAR + 8 * B_P1, 0);
  const uint32_t oa = sb + OFF_OA + (lane >> 4) * 2048 + (32 * w + 2 * (lane & 15) + par) * 16;
#pragma unroll
  for (int j = 0; j < 5; j++) stsm4(oa + 4096 * j, ov + 4 * j);
  TSIF(par == 0 && w == 0, 120);
  fence_async_smem();
  TSIF(par == 0 && w == 0, 121);
  __syncwarp();
  if (lane == 0) mbar_arrive(sb + OFF_BAR + 8 * B_ATTN);
  TSM(w == 0 || w == 2, 122 + par + (w == 2 ? 3 : 0));
  wg_wait<0>();
  pin<32>(X);
  twiddle_fwd(fa, X, fc);
}

struct Maps {
  CUtensorMap x, wm, wt, k, v, y, wo, qm, qt, om, ot, yl, ol, wh;
};

__device__ __forceinline__ void load_stage(uint32_t sb, int kb, int b, const Maps& m) {
  const uint32_t st = sb + (kb & 3) * STAGE_BYTES, bar = sb + OFF_BAR + 8 * (B_FULL1 + (kb & 3));
  const int r = b >> 3, hg = b & 7, slab = kb - KV_KB;
  const bool kv = slab >= 0 && slab < 5;
  const uint32_t kbar = sb + OFF_BAR + 8 * (B_KV + slab), dst = sb + OFF_KVS + slab * KVS_BYTES;
  mbar_expect_tx(bar, STAGE_BYTES);
  if (kv) mbar_expect_tx(kbar, KVS_BYTES);
  tma_3d(st, &m.x, 64 * kb, 64 * r, 0, bar);
  tma_3d(st + ST_W, &m.wm, 80 * hg + (tail_first(hg) ? 16 : 0), 64 * kb, 0, bar);
  tma_3d(st + ST_WT, &m.wt, 80 * hg + (tail_first(hg) ? 0 : 64), 64 * kb, 0, bar);
  if (kv) tma_3d(dst, &m.k, 0, 32 * (b >> 1) - 3, 2 * slab + (b & 1), kbar);
  if (kv) tma_3d(dst + KVS_V, &m.v, 0, 32 * (b >> 1), 2 * slab + (b & 1), kbar);
}

__global__ void __launch_bounds__(NTHR, 1) fused_kernel(const __grid_constant__ Maps m, const Params p) {
  extern __shared__ __align__(1024) uint8_t smem[];
  const uint32_t sb = (uint32_t)__cvta_generic_to_shared(smem);
  const uint32_t bars = sb + OFF_BAR;
  const int tid = threadIdx.x, lane = tid & 31;
  int b = blockIdx.x;
  b = (((b & 63) >> 3) * 2 + (b & 1)) * 8 + (((b < 64 ? 0x6521 : 0x7430) >> (4 * ((b >> 1) & 3))) & 7);
  const int r = b >> 3, hg = b & 7;

  if (tid == T_ISSUE) {
    TSM(true, 0);
#pragma unroll
    for (int i = 0; i < 4; i++) mbar_init(bars + 8 * (B_F0 + i), 1);
    fence_async_smem();
#pragma unroll
    for (int i = 0; i < 4; i++) {
      mbar_expect_tx(bars + 8 * (B_F0 + i), (i ? 0 : ST_W) + 6144);
      if (i == 0) tma_3d(sb, &m.x, 0, 64 * r, 0, bars + 8 * B_F0);
      tma_3d(sb + ST_W + 6144 * i, &m.wh, 80 * hg + (tail_first(hg) ? 16 : 0), 16 * i, 0, bars + 8 * (B_F0 + i));
    }
#pragma unroll
    for (int i = 0; i < 4; i++) mbar_init(bars + 8 * (B_FULL1 + i), 1);
    fence_async_smem();
    mbar_expect_tx(bars + 8 * B_FULL1, STAGE_BYTES - ST_WT);
    tma_3d(sb + ST_WT, &m.wt, 80 * hg + (tail_first(hg) ? 0 : 64), 0, 0, bars + 8 * B_FULL1);
    load_stage(sb, 1, b, m);
  } else if (tid == T_INIT) {
#pragma unroll
    for (int i = 0; i < B_F0; i++) mbar_init(bars + 8 * i, i < B_GATE ? 8 : i < B_CVD ? 4 : i == B_CVD ? 20 : 1);
    fence_async_smem();
  }
  const int warp = __shfl_sync(0xffffffffu, tid >> 5, 0), wg = warp >> 2, w = warp & 3;
  __syncthreads();

  if (wg == 3) {
    asm volatile("setmaxnreg.dec.sync.aligned.u32 56;");
    if (w == 0) {
      if (lane == 0) {
#pragma unroll 1
        for (int kb = 2; kb < 10; kb++) {
          if (kb >= 4) mbar_wait(bars + 8 * (kb == 7 ? B_E3 : B_EMPTY1 + (kb & 3)), (kb >> 3) & 1);
          TSIF(kb >= 4, 44 + kb);
          load_stage(sb, kb, b, m);
          TSIF(kb == 3, 60);
          if (kb == 9) mbar_arrive(bars + 8 * B_LAST);
        }
        mbar_wait(bars + 8 * B_WOP, 0);
        mbar_wait(bars + 8 * B_EPOCH, 0);
        flag_wait(g_cnt + C_W + 32 * hg, (lds32(sb + OFF_EPOCH) + 1) * 16);
        TS(30);
#pragma unroll 1
        for (int j = 0; j < 8; j++) {
          if (j >= 6) mbar_wait(bars + 8 * (B_EMPTY2 + j - 6), 0);
          if (j == 4) mbar_wait(bars + 8 * B_ORB, 0);
          TSIF(j >= 6, 100 + j);
          mbar_expect_tx(bars + 8 * (B_FULL2 + j), j == 0 ? WO_BYTES : j == 5 ? O_BYTES + WO_BYTES + 512 : O_BYTES + WO_BYTES);
          bulk_load(sb + off_w(j), g_WO + (hg * 8 + step_src(hg, j)) * 800, WO_BYTES, bars + 8 * (B_FULL2 + j));
        }
        mbar_wait(bars + 8 * (B_EMPTY2 + 3), 0);
        mbar_expect_tx(bars + 8 * B_QF, O_BYTES);
        tma_2d(sb + OFF_QS, &m.qm, 80 * hg, 128 * r, bars + 8 * B_QF);
        tma_2d(sb + OFF_QT, &m.qt, 80 * hg + 64, 128 * r, bars + 8 * B_QF);
      }
    } else if (w == 1) {
      unsigned epoch = 0;
      if (lane == 0) {
        epoch = atomicAdd(g_cnt + C_LAUNCH, 1u) / NCTA;
        asm volatile("st.shared.u32 [%0], %1;" ::"r"(sb + OFF_EPOCH), "r"(epoch) : "memory");
        mbar_arrive(bars + 8 * B_EPOCH);
        mbar_wait(bars + 8 * B_KVD, 0);
        mbar_expect_tx(bars + 8 * B_HB, 5 * 4096);
#pragma unroll 1
        for (int c = 0; c < 5; c++) {
          if (c == 3) mbar_wait(bars + 8 * B_S3, 0);
          bulk_load(sb + off_ch(c) + U_BYTES, p.ssm_k + (5 * b + c) * SEQ, 4096, bars + 8 * B_HB);
        }
#pragma unroll
        for (int c = 0; c < 4; c++) mbar_expect_tx(bars + 8 * (B_U + c), c < 3 ? U_BYTES : 2 * U_BYTES);
        const uint4* usrc = g_U + 5 * b * U_PITCH;
        mbar_wait(bars + 8 * B_USIG, 0);
        flag_wait(g_cnt + C_PREP + 32 * (b & 15), (epoch + 1) * NCTA);
        TS(23);
#pragma unroll
        for (int c = 0; c < 5; c++) {
          if (c == 3) mbar_wait(bars + 8 * (B_U + 2), 0);
          bulk_load(sb + off_ch(c), usrc + c * U_PITCH, U_BYTES, bars + 8 * (B_U + (c < 3 ? c : 3)));
          TSIF(c == 0 || c == 4, 116 + (c >> 2));
        }
      }
      epoch = __shfl_sync(0xffffffffu, epoch, 0);
      if (lane < 8) {
        const int src = (b & ~7) | step_src(hg, lane);
        mbar_wait(bars + 8 * B_ATTN, 0);
        TS(20);
        bool seen = false;
#pragma unroll 1
        for (int spins = 0; spins < SPIN_LIMIT; spins++) {
          const bool now = !seen && (int)(flag_read(g_cnt + C_O + 32 * src) - (epoch + 1)) >= 0;
          if (now && lane >= 1 && lane < 4) bulk_load(sb + off_o(lane), g_O + src * 1280, O_BYTES, bars + 8 * (B_FULL2 + lane));
          seen = seen || now;
          if (__all_sync(0xff, seen)) break;
        }
        TS(21);
        if (lane == 5) bulk_load(sb + OFF_GATE, g_gate + 128 * r, 512, bars + 8 * (B_FULL2 + 5));
#pragma unroll 1
        for (int j = 4; j < 8; j++) {
          if (lane == j) {
            mbar_wait(bars + 8 * (j < 6 ? B_C34 : B_EMPTY2 + j - 6), 0);
            bulk_load(sb + off_o(j), g_O + src * 1280, O_BYTES, bars + 8 * (B_FULL2 + j));
          }
          __syncwarp(0xff);
        }
        TS(22);
      }
    } else if (w == 2) {
      mbar_wait(bars + 8 * B_PREP, 0);
      flag_signal(g_cnt + C_PREP, 16, lane);
      TS(25);
      if (lane == 0) {
        mbar_arrive(bars + 8 * B_USIG);
        mbar_expect_tx(bars + 8 * B_ORB, O_BYTES / 4 + 64);
        mbar_wait(bars + 8 * B_GATE, 0);
        publish(g_gate + 16 * b, sb + OFF_GATE + 64 * hg, 64);
        bulk_load(sb + OFF_GATE + 64 * hg, g_gate + 16 * b, 64, bars + 8 * B_ORB);
        mbar_wait(bars + 8 * B_ATTN, 0);
        publish(g_O + b * 1280, sb + OFF_OA, O_BYTES);
        tma_2d(sb + OFF_KVX + 10240, &m.ol, 48, b * 160, bars + 8 * B_ORB);
        TS(74);
        mbar_wait(bars + 8 * B_ORB, 0);
        flag_bump(g_cnt + C_O + 32 * b);
        TS(26);
      }
    } else {
      if (lane == 0) {
        uint4* dst = g_WO + (hg * 8 + (r >> 1)) * 800 + (r & 1) * 80;
        mbar_wait(bars + 8 * B_S3, 0);
        asm volatile("cp.async.bulk.prefetch.L2.global [%0], 6400;" ::"l"(p.wo + b * 3200) : "memory");
        mbar_wait(bars + 8 * B_P1, 0);
        mbar_wait(bars + 8 * WB_TRIG, 0);
        mbar_expect_tx(bars + 8 * B_WST, WO_BYTES / 2);
        tma_3d(sb + OFF_WA, &m.wo, 0, 40 * r, 5 * hg, bars + 8 * B_WST);
        mbar_wait(bars + 8 * B_WST, 0);
#pragma unroll 1
        for (int n = 0; n < 5; n++) bulk_store(dst + 160 * n, sb + OFF_WA + 1280 * n, 1280);
        bulk_wait_read();
        mbar_expect_tx(bars + 8 * B_WST, WO_BYTES / 2);
#pragma unroll 1
        for (int n = 0; n < 5; n++) bulk_load(sb + OFF_WA + 1280 * n, dst + 160 * n, 1280, bars + 8 * B_WST);
        mbar_wait(bars + 8 * B_WST, 1);
        flag_bump(g_cnt + C_W + 32 * hg);
        mbar_arrive(bars + 8 * B_WOP);
        TS(71);
        mbar_expect_tx(bars + 8 * B_C34, 3 * (U_BYTES / 4));
        mbar_expect_tx(bars + 8 * B_YRB, 2 * (U_BYTES / 4));
#pragma unroll 1
        for (int c = 0; c < 5; c++) {
          mbar_wait(bars + 8 * (B_YST + c), 0);
          publish(g_U + (5 * b + c) * U_PITCH, sb + off_ch(c), U_BYTES);
          tma_2d(sb + off_ch(c), &m.yl, 48, (5 * b + c) * (U_PITCH / 8), bars + 8 * (c < 3 ? B_C34 : B_YRB));
        }
        TS(75);
        mbar_wait(bars + 8 * B_C34, 0);
        mbar_wait(bars + 8 * B_YRB, 0);
        flag_bump(g_cnt + C_Y + 32 * (b >> 4));
        TS(27);
        mbar_expect_tx(bars + 8 * B_YFULL, 20480);
        flag_wait(g_cnt + C_Y + 32 * hg, (lds32(sb + OFF_EPOCH) + 1) * 16);
        TS(24);
        tma_2d(sb + OFF_YT, &m.y, 128 * r, 80 * hg, bars + 8 * B_YFULL);
        tma_2d(sb + OFF_YT + 10240, &m.y, 128 * r + 64, 80 * hg, bars + 8 * B_YFULL);
      }
    }
  } else {
    asm volatile("setmaxnreg.inc.sync.aligned.u32 152;");
    FftConst fc;
    uint32_t fa[4][4];
    if (wg < 2) {
      float acc[120];
#pragma unroll
      for (int i = 0; i < 120; i++) acc[i] = 0.f;
      const uint32_t da = desc_lo(sb + wg * 8192, 16), db = desc_lo(sb + ST_W, 8192), dc = desc_lo(sb + ST_WT, 2048);
#pragma unroll
      for (int k = 0; k < 4; k++) {
        mbar_wait(bars + 8 * (B_F0 + k), 0);
        TSIF(w == 0 && wg == 0 && k == 0, 1);
        wg_fence();
        WgSST<192>::mma<HI_SW128, HI_SW128>(acc, da + 2 * k, desc_lo(sb + ST_W, 2048) + 384 * k, 1);
        wg_commit();
      }
      mbar_wait(bars + 8 * B_FULL1, 0);
      wg_fence();
#pragma unroll
      for (int k = 0; k < 4; k++) WgSST<48>::mma<HI_SW128, HI_SW32>(acc + 96, da + 2 * k, dc + 32 * k, 1);
      wg_commit();
#pragma unroll 1
      for (int kb = 1; kb < 10; kb++) {
        mbar_wait(bars + 8 * (B_FULL1 + (kb & 3)), (kb >> 2) & 1);
        const uint32_t so = (kb & 3) * (STAGE_BYTES >> 4);
        wg_fence();
#pragma unroll
        for (int k = 0; k < 4; k++) {
          WgSST<192>::mma<HI_SW128, HI_SW128>(acc, da + so + 2 * k, db + so + 128 * k, 1);
          WgSST<48>::mma<HI_SW128, HI_SW32>(acc + 96, da + so + 2 * k, dc + so + 32 * k, 1);
        }
        wg_commit();
        wg_wait<1>();
        if (lane == 0) mbar_arrive(bars + 8 * (kb == 4 ? B_E3 : B_EMPTY1 + ((kb - 1) & 3)));
      }
      mbar_wait(bars + 8 * B_EPOCH, 0);
      const uint32_t tag = lds32(sb + OFF_EPOCH) + 1;
      mbar_wait(bars + 8 * B_S3, 0);
      wg_wait<0>();
      pin<120>(acc);
      if (lane == 0) mbar_arrive(bars + 8 * B_P1);
      TSM(w == 0, 3 + wg);
      attention(acc, sb, b, wg, w, lane, tag, fc, fa);
    } else {
      const int tw = tid & 127, chl = 64 * (b & 1) + 8 * w + (lane >> 2);
      uint4* up = g_U + chl * U_PITCH + ((4 * (b >> 1) + (lane & 3)) ^ ((b >> 2) & 1));
      uint2 sw[10];
      uint32_t dv = 0;
      if (lane < 5) dv = __ldg(reinterpret_cast<const unsigned short*>(p.ssm_D) + 5 * b + lane);
#pragma unroll
      for (int i = 0; i < 10; i++) sw[i] = ldg64(reinterpret_cast<const uint2*>(p.shift_k) + chl + 128 * (i >> 1) + 32 * (i & 1));
      uint32_t tab[12];
      uint32_t tt[2];
      fft_tables(tab, tw);
      fft_twiddles(tt, tw);
      uint4 res[10];
#pragma unroll
      for (int i = 0; i < 10; i++) res[i] = make_uint4(0, 0, 0, 0);
#pragma unroll 1
      for (int slab = 0; slab < 5; slab++) {
#pragma unroll
        for (int i = 0; i < 8; i++) res[i] = res[i + 2];
        prep_slab(res + 8, sw, sb, slab, w, lane);
        TSIF(w == 0, 99 + 4 * slab);
#pragma unroll
        for (int i = 0; i < 8; i++) sw[i] = sw[i + 2];
      }
      TSIF(w == 0, 28);
      __syncwarp();
      if (lane == 0) mbar_arrive(bars + 8 * B_KVD + ((res[8].x ^ res[9].x) & p.zero));
      mbar_wait(bars + 8 * B_KVD, 0);
      fft_tables_store(tab, sb, tw);
      mbar_wait(bars + 8 * B_LAST, 0);
#pragma unroll
      for (int i = 0; i < 10; i++) up[(128 * (i >> 1) + 32 * (i & 1)) * U_PITCH] = res[i];
      __syncwarp();
      if (lane == 0) mbar_arrive(bars + 8 * B_PREP);
      TSIF(w == 0, 5);
      mbar_wait(bars + 8 * B_LAST, 0);
      prep_gate(p, sb, b, w, lane);
      __syncwarp();
      if (lane == 0) mbar_arrive(bars + 8 * B_GATE);
      TSIF(w == 0, 72);
      mbar_wait(bars + 8 * B_HB, 0);
      TSIF(w == 0, 2);
      const uint32_t ha = sb + U_BYTES + ((tw >> 3) * 16 + 8 + (tw & 7)) * 16;
      uint4 hv[5];
#pragma unroll
      for (int c = 0; c < 5; c++) hv[c] = lds128(ha + off_ch(c));
      __syncwarp();
#pragma unroll
      for (int c = 0; c < 5; c++) sts128((ha ^ 16) + off_ch(c), hv[c].x, hv[c].y, hv[c].z, hv[c].w);
      asm volatile("st.shared.v2.u32 [%0], {%1, %2};" ::"r"(sb + OFF_TT + 8 * tw), "r"(tt[0]), "r"(tt[1]) : "memory");
      if (tw < 5) asm volatile("st.shared.f32 [%0], %1;" ::"r"(sb + OFF_D + 4 * tw), "f"(bf_lo(dv) * 0.125f) : "memory");
      fence_async_smem();
      __syncwarp();
      if (lane == 0) mbar_arrive(bars + 8 * B_HA);
      TSIF(w == 0, 6);
      if (FC_AT) {
        mbar_wait(bars + 8 * B_HA, 0);
        fft_matrices(fc, sb, w, lane);
      }
      float X[32];
      wg_fence();
      f_step(X, fc, desc_h(sb, TASK2));
      wg_wait<0>();
      pin<32>(X);
      twiddle_fwd(fa, X, fc);
    }

    TSM(w == 0 && wg == 0, 104);
    if (!FC_AT) {
      mbar_wait(bars + 8 * B_HA, 0);
      fft_matrices(fc, sb, w, lane);
    }
    TSM(w == 0 && wg == 0, 105);
    TSM(w == 0 && wg == 2, 124);
#pragma unroll 1
    for (uint32_t tasks = wg == 0 ? TASK0 : wg == 1 ? TASK1 : TASK2; tasks; tasks >>= 4) {
      const int c = (tasks & 7) - 1;
      conv_channel(fc, fa, sb, c, tasks >> 4, wg, w, lane);
      if (lane == 0) mbar_arrive(bars + 8 * (B_YST + c));
      TSM(w == 0, 10 + c);
    }

    if (wg != 1) {
      const int wg = warp >> 3;
      const int g = lane >> 2;
      float acc[40];
#pragma unroll
      for (int i = 0; i < 40; i++) acc[i] = 0.f;
      const uint32_t da = desc_lo(sb + wg * 1024, 2048), db = desc_lo(sb, 2560);
      mbar_wait(bars + 8 * B_ORB, 0);
      mbar_wait(bars + 8 * B_FULL2, 0);
      TSM(w == 0, 15 + wg);
#pragma unroll 1
      for (int j = 0; j < 8; j++) {
        if (j == 1 - wg) mbar_wait(bars + 8 * B_CVD, 0);
        mbar_wait(bars + 8 * (B_FULL2 + j), 0);
        TSM(w == 0 && wg == 0, 44 + (j < 4 ? j : j + 6));
        const uint32_t oa = da + (off_o(j) >> 4), ob = db + (off_w(j) >> 4);
        wg_fence();
#pragma unroll
        for (int k = 0; k < 5; k++) WgSST<80>::mma<HI_NONE, HI_SW32>(acc, oa + 256 * k, ob + 32 * k, 1);
        wg_commit();
        wg_wait<1>();
        if (j >= 1 && j <= 4 && lane == 0) mbar_arrive(bars + 8 * (B_EMPTY2 + j - 1));
      }
      TSIF(w == 0 && wg == 0, 113);
      const int tr = 64 * wg + 16 * w + (lane & 15);
      const uint32_t fm = sb + OFF_QS + tr * 128, fx = (lane >> 4) ^ (tr & 7);
      const uint32_t ft = sb + OFF_QT + tr * 32 + (((lane >> 4) ^ (tr >> 2)) & 1) * 16;
      const float g0 = __uint_as_float(lds32(sb + OFF_GATE + (64 * wg + 16 * w + g) * 4));
      const float g1 = __uint_as_float(lds32(sb + OFF_GATE + (64 * wg + 16 * w + 8 + g) * 4));
      const uint32_t ga = pack2(g0, g0), gb = pack2(g1, g1);
      const uint32_t na = pack2(1.f - g0, 1.f - g0), nb = pack2(1.f - g1, 1.f - g1);

      uint32_t qf[20];
      mbar_wait(bars + 8 * B_QF, 0);
      TSM(w == 0 && wg == 0, 99);
#pragma unroll
      for (int j = 0; j < 5; j++) ldsm4(qf + 4 * j, j < 4 ? fm + ((fx ^ (2 * j)) << 4) : ft);
#pragma unroll
      for (int i = 0; i < 20; i++) {
        qf[i] = bmul((i & 1) ? gb : ga, qf[i]);
        asm volatile("" : "+r"(qf[i]));
      }

      wg_wait<0>();
      pin<40>(acc);
      TSM(w == 0, 17 + wg);
      uint32_t pb[20];
#pragma unroll
      for (int j = 0; j < 10; j++) {
        pb[2 * j] = bmul(na, pack2(acc[4 * j], acc[4 * j + 1]));
        pb[2 * j + 1] = bmul(nb, pack2(acc[4 * j + 2], acc[4 * j + 3]));
        asm volatile("" : "+r"(pb[2 * j]), "+r"(pb[2 * j + 1]));
      }
      const uint32_t ya = sb + OFF_YT + wg * 10240 + ((lane >> 4) * 8 + (lane & 7)) * 128 +
                          (((2 * w + (((lane >> 3) & 1) ^ wg)) ^ (lane & 7)) << 4);
      mbar_wait(bars + 8 * B_YFULL, 0);
      TSM(w == 0 && wg == 0, 19);
#pragma unroll
      for (int j = 0; j < 5; j++) {
        uint32_t y[4];
        ldsm4t(y, ya + 2048 * j);
#pragma unroll
        for (int i = 0; i < 4; i++)
          qf[4 * j + i] = bfma(qf[4 * j + i], y[i], pb[4 * j + i]);
      }
#pragma unroll
      for (int j = 0; j < 5; j++) stsm4(j < 4 ? fm + ((fx ^ (2 * j)) << 4) : ft, qf + 4 * j);
      fence_async_smem();
      __syncwarp();
      if (lane == 0) {
        const int row = 64 * wg + 16 * w;
        asm volatile("cp.async.bulk.tensor.2d.global.shared::cta.bulk_group [%0, {%2, %3}], [%1];"
                     ::"l"(&m.om), "r"(sb + OFF_QS + row * 128), "r"(80 * hg), "r"(128 * r + row) : "memory");
        asm volatile("cp.async.bulk.tensor.2d.global.shared::cta.bulk_group [%0, {%2, %3}], [%1];"
                     ::"l"(&m.ot), "r"(sb + OFF_QT + row * 32), "r"(80 * hg + 64), "r"(128 * r + row) : "memory");
        asm volatile("cp.async.bulk.commit_group;\ncp.async.bulk.wait_group.read 0;" ::: "memory");
      }
      TSM(w == 0 || w == 3, 40 + 2 * wg + (w & 1));
    }
  }
}

typedef CUresult (*EncodeFn)(CUtensorMap*, CUtensorMapDataType, cuuint32_t, void*, const cuuint64_t*, const cuuint64_t*,
                             const cuuint32_t*, const cuuint32_t*, CUtensorMapInterleave, CUtensorMapSwizzle,
                             CUtensorMapL2promotion, CUtensorMapFloatOOBfill);

void encode(EncodeFn fn, CUtensorMap* tm, const void* base, int rank, const cuuint64_t* dims, const cuuint64_t* strides,
            const cuuint32_t* box, CUtensorMapSwizzle swz) {
  const cuuint32_t ones[3] = {1, 1, 1};
  fn(tm, CU_TENSOR_MAP_DATA_TYPE_BFLOAT16, rank, const_cast<void*>(base), dims, strides, box, ones,
     CU_TENSOR_MAP_INTERLEAVE_NONE, swz, CU_TENSOR_MAP_L2_PROMOTION_L2_128B, CU_TENSOR_MAP_FLOAT_OOB_FILL_NONE);
}

}

extern "C" void kernel_launch(void* const* d_in, const int* in_sizes, int n_in, void* d_out, int out_size) {
  (void)in_sizes; (void)n_in; (void)out_size;
  Params p;
  p.q = (const __nv_bfloat16*)d_in[0];
  p.k = (const __nv_bfloat16*)d_in[1];
  p.v = (const __nv_bfloat16*)d_in[2];
  p.shift_k = (const __nv_bfloat16*)d_in[3];
  p.ssm_k = (const __nv_bfloat16*)d_in[4];
  p.ssm_D = (const __nv_bfloat16*)d_in[5];
  p.wqkv = (const __nv_bfloat16*)d_in[7];
  p.wo = (const __nv_bfloat16*)d_in[8];
  p.gate_w = (const __nv_bfloat16*)d_in[9];
  p.out = (__nv_bfloat16*)d_out;
  p.zero = 0;

  static EncodeFn fn = nullptr;
  static void *yaddr = nullptr, *oaddr = nullptr;
  if (!fn) {
    cudaDriverEntryPointQueryResult qr;
    void* f = nullptr;
    cudaGetDriverEntryPoint("cuTensorMapEncodeTiled", &f, cudaEnableDefault, &qr);
    fn = (EncodeFn)f;
    cudaGetSymbolAddress(&yaddr, g_U);
    cudaGetSymbolAddress(&oaddr, g_O);
    cudaFuncSetAttribute(fused_kernel, cudaFuncAttributeMaxDynamicSharedMemorySize, SMEM_BYTES);
  }
  Maps m;
  {
    const cuuint64_t dims[3] = {640, 1024, 2}, st[2] = {2560, 1280};
    const cuuint32_t box[3] = {64, 64, 2};
    encode(fn, &m.x, p.q, 3, dims, st, box, CU_TENSOR_MAP_SWIZZLE_128B);
  }
  {
    const cuuint64_t dims[3] = {640, 640, 3}, st[2] = {3840, 1280};
    const cuuint32_t box[3] = {64, 64, 3}, boxt[3] = {16, 64, 3};
    encode(fn, &m.wm, p.wqkv, 3, dims, st, box, CU_TENSOR_MAP_SWIZZLE_128B);
    encode(fn, &m.wt, p.wqkv, 3, dims, st, boxt, CU_TENSOR_MAP_SWIZZLE_32B);
    const cuuint32_t boxh[3] = {64, 16, 3};
    encode(fn, &m.wh, p.wqkv, 3, dims, st, boxh, CU_TENSOR_MAP_SWIZZLE_128B);
  }
  {
    const cuuint64_t dims[3] = {64, 2048, 10}, st[2] = {1280, 128};
    const cuuint32_t boxk[3] = {64, 35, 1}, boxv[3] = {64, 32, 1};
    encode(fn, &m.k, p.k, 3, dims, st, boxk, CU_TENSOR_MAP_SWIZZLE_128B);
    encode(fn, &m.v, p.v, 3, dims, st, boxv, CU_TENSOR_MAP_SWIZZLE_128B);
  }
  {
    const cuuint64_t dims[3] = {16, 640, 40}, st[2] = {1280, 32};
    const cuuint32_t box[3] = {16, 40, 5};
    encode(fn, &m.wo, p.wo, 3, dims, st, box, CU_TENSOR_MAP_SWIZZLE_32B);
  }
  {
    const cuuint64_t dims[2] = {2048, 640}, st[1] = {U_PITCH * 16};
    const cuuint32_t box[2] = {64, 80};
    encode(fn, &m.y, yaddr, 2, dims, st, box, CU_TENSOR_MAP_SWIZZLE_128B);
    const cuuint64_t dl[2] = {64, DIM * U_PITCH / 8}, dol[2] = {64, NCTA * 160}, sl[1] = {128};
    const cuuint32_t bl[2] = {16, 32}, bol[2] = {16, 160};
    encode(fn, &m.yl, yaddr, 2, dl, sl, bl, CU_TENSOR_MAP_SWIZZLE_NONE);
    encode(fn, &m.ol, oaddr, 2, dol, sl, bol, CU_TENSOR_MAP_SWIZZLE_NONE);
  }
  {
    const cuuint64_t dims[2] = {640, 2048}, st[1] = {1280};
    const cuuint32_t bqm[2] = {64, 128}, bqt[2] = {16, 128}, bom[2] = {64, 16}, bot[2] = {16, 16};
    encode(fn, &m.qm, p.q, 2, dims, st, bqm, CU_TENSOR_MAP_SWIZZLE_128B);
    encode(fn, &m.qt, p.q, 2, dims, st, bqt, CU_TENSOR_MAP_SWIZZLE_32B);
    encode(fn, &m.om, p.out, 2, dims, st, bom, CU_TENSOR_MAP_SWIZZLE_128B);
    encode(fn, &m.ot, p.out, 2, dims, st, bot, CU_TENSOR_MAP_SWIZZLE_32B);
  }
  fused_kernel<<<NCTA, NTHR, SMEM_BYTES>>>(m, p);
}
```

```cpp
#include <cuda.h>
#include <cuda_bf16.h>
#include <cuda_runtime.h>
#include <stdint.h>

namespace {

constexpr int SEQ = 2048, DIM = 640, NCTA = 128, NTHR = 512;

#define KV_KB 2
#define DEV_EXIT 0
#define FENCE_LO 0
#define FENCE_HI 0
#define WB_TRIG B_USIG
#define T_ISSUE 288
#define T_INIT 448
#define TASK0 0x3
#define TASK1 0x52
#define TASK2 0x41

constexpr uint32_t STAGE_BYTES = 47104, ST_W = 16384, ST_WT = 40960;
constexpr uint32_t O_BYTES = 20480, WO_BYTES = 12800;
constexpr uint32_t OFF_OA = 0;
constexpr uint32_t OFF_QS = 3 * O_BYTES, OFF_QT = OFF_QS + 16384;
constexpr uint32_t OFF_WC = 81920;
constexpr uint32_t OFF_WA = 94720;
constexpr uint32_t OFF_GATE = 145920;
constexpr uint32_t OFF_TT = 146432;
constexpr uint32_t OFF_KVX = 148480;
constexpr uint32_t OFF_CH3 = 163840;
constexpr uint32_t CH_BYTES = 12288, U_BYTES = 4096;
constexpr uint32_t OFF_FT = 225280, OFF_GT = 229376;
constexpr uint32_t OFF_CH0 = 188416;
constexpr uint32_t OFF_KVS = OFF_CH0, KVS_V = 4480, KVS_BYTES = 8576;
constexpr uint32_t OFF_YT = 163840;
constexpr uint32_t OFF_BAR = 231936;
constexpr uint32_t SMEM_BYTES = OFF_BAR + 512;

enum : uint32_t {
  B_EMPTY1 = 0, B_S3 = 3, B_E3 = 4, B_EMPTY2 = 5, B_ATTN = 9, B_P1 = 10,
  B_GATE = 11, B_HA = 12, B_KVD = 13, B_PREP = 14, B_YST = 15,
  B_CVD = 20,
  B_FULL2 = 21, B_U = 29, B_KV = 33, B_HB = 38, B_C34 = 39, B_YRB = 40, B_YFULL = 41, B_EPOCH = 42, B_LAST = 43,
  B_WOP = 44, B_USIG = 45, B_WST = 46, B_QF = 47, B_ORB = 48,
  B_F0 = 49, B_FULL1 = 53
};
constexpr uint32_t OFF_EPOCH = OFF_BAR + 8 * 58, OFF_D = OFF_BAR + 8 * 60;
__device__ __forceinline__ uint32_t off_o(int j) { return j < 4 ? OFF_OA + j * O_BYTES : j < 6 ? OFF_CH0 + (j - 4) * O_BYTES : OFF_OA + (j - 6) * O_BYTES; }
__device__ __forceinline__ uint32_t off_w(int j) { return j < 4 ? OFF_WA + j * WO_BYTES : j == 4 ? OFF_KVX : j == 5 ? OFF_WC : OFF_WA + (j - 6) * WO_BYTES; }
__device__ __forceinline__ int step_src(int hg, int j) { return j == 0 ? hg : j <= hg ? j - 1 : j; }
__device__ __forceinline__ bool tail_first(int hg) { return (hg & 3) == 3; }
__device__ __forceinline__ uint32_t off_ch(int c) { return (c < 3 ? OFF_CH0 : OFF_CH3 - 3 * CH_BYTES) + c * CH_BYTES; }

#define U_PITCH 264
__device__ __align__(1024) uint4 g_U[DIM * U_PITCH];
__device__ __align__(128) uint4 g_O[NCTA * 1280];
__device__ uint4 g_WO[64 * 800];
__device__ uint4 g_halo[NCTA * 2 * 7 * 32];
__device__ __align__(128) float g_gate[SEQ];
__device__ unsigned g_cnt[32 * (1 + 2 * 16 + 8 + NCTA)];
constexpr int C_LAUNCH = 0, C_PREP = 32, C_Y = 32 * 17, C_W = 32 * 33, C_O = 32 * 41;

#define TSM(cond, slot) do { } while (0)
#define TSIF(cond, slot) do { if (__LINE__ >= FENCE_LO && __LINE__ < FENCE_HI) sched_fence(); } while (0)
__device__ __forceinline__ void sched_fence() {
  asm volatile("{\n.reg .pred p;\n.reg .u32 c;\nmov.u32 c, %%clock;\nsetp.eq.u32 p, c, 0;\n@p st.shared.u32 [%0], c;\n}"
               ::"r"(1024 + OFF_EPOCH + 4) : "memory");
}
#define TS(slot) TSIF(true, slot)

struct Params {
  const __nv_bfloat16 *q, *k, *v, *shift_k, *ssm_k, *ssm_D, *wqkv, *wo, *gate_w;
  __nv_bfloat16* out;
  uint32_t zero;
};

constexpr int SPIN_LIMIT = 1 << 17;

__device__ __forceinline__ void mbar_init(uint32_t bar, uint32_t count) {
  asm volatile("mbarrier.init.shared::cta.b64 [%0], %1;" ::"r"(bar), "r"(count) : "memory");
}
__device__ __forceinline__ void mbar_expect_tx(uint32_t bar, uint32_t bytes) {
  asm volatile("mbarrier.arrive.expect_tx.shared::cta.b64 _, [%0], %1;" ::"r"(bar), "r"(bytes) : "memory");
}
__device__ __forceinline__ void mbar_arrive(uint32_t bar) {
  asm volatile("mbarrier.arrive.shared::cta.b64 _, [%0];" ::"r"(bar) : "memory");
}
__device__ __forceinline__ void mbar_wait(uint32_t bar, uint32_t parity) {
  uint32_t ok;
  int spins = 0;
  do {
      asm volatile("{\n.reg .pred p;\nmbarrier.try_wait.parity.shared::cta.b64 p, [%1], %2;\nselp.b32 %0, 1, 0, p;\n}"
                   : "=r"(ok) : "r"(bar), "r"(parity) : "memory");
    if (++spins > SPIN_LIMIT) break;
  } while (!ok);
}
__device__ __forceinline__ unsigned flag_read(const unsigned* p) {
  unsigned v;
  asm volatile("ld.relaxed.gpu.global.u32 %0, [%1];" : "=r"(v) : "l"(p) : "memory");
  return v;
}
__device__ __forceinline__ void flag_poll(const unsigned* p, unsigned target) {
  unsigned v;
  int spins = 0;
  do {
    asm volatile("ld.relaxed.gpu.global.u32 %0, [%1];" : "=r"(v) : "l"(p) : "memory");
    if (++spins > SPIN_LIMIT) break;
  } while ((int)(v - target) < 0);
}
__device__ __forceinline__ void flag_wait(const unsigned* p, unsigned target) {
  flag_poll(p, target);
}
__device__ __forceinline__ void flag_signal(unsigned* p, int n, int lane) {
  if (lane == 0) asm volatile("fence.release.gpu;" ::: "memory");
  __syncwarp();
  if (lane < n) asm volatile("red.relaxed.gpu.global.add.u32 [%0], 1;" ::"l"(p + 32 * lane) : "memory");
}
__device__ __forceinline__ void flag_bump(unsigned* p) {
  asm volatile("red.relaxed.gpu.global.add.u32 [%0], 1;" ::"l"(p) : "memory");
}
__device__ __forceinline__ void fence_async_smem() { asm volatile("fence.proxy.async.shared::cta;" ::: "memory"); }
__device__ __forceinline__ void wg_sync(int id) { asm volatile("bar.sync %0, 128;" ::"r"(id) : "memory"); }

__device__ __forceinline__ void tma_2d(uint32_t dst, const CUtensorMap* tm, int c0, int c1, uint32_t bar) {
  asm volatile("cp.async.bulk.tensor.2d.shared::cluster.global.mbarrier::complete_tx::bytes [%0], [%1, {%3, %4}], [%2];"
               ::"r"(dst), "l"(tm), "r"(bar), "r"(c0), "r"(c1) : "memory");
}
__device__ __forceinline__ void tma_3d(uint32_t dst, const CUtensorMap* tm, int c0, int c1, int c2, uint32_t bar) {
  asm volatile("cp.async.bulk.tensor.3d.shared::cluster.global.mbarrier::complete_tx::bytes [%0], [%1, {%3, %4, %5}], [%2];"
               ::"r"(dst), "l"(tm), "r"(bar), "r"(c0), "r"(c1), "r"(c2) : "memory");
}
__device__ __forceinline__ void bulk_load(uint32_t dst, const void* src, uint32_t bytes, uint32_t bar) {
  asm volatile("cp.async.bulk.shared::cluster.global.mbarrier::complete_tx::bytes [%0], [%1], %2, [%3];"
               ::"r"(dst), "l"(src), "r"(bytes), "r"(bar) : "memory");
}
__device__ __forceinline__ void bulk_store(void* dst, uint32_t src, uint32_t bytes) {
  asm volatile("cp.async.bulk.global.shared::cta.bulk_group [%0], [%1], %2;" ::"l"(dst), "r"(src), "r"(bytes) : "memory");
}
__device__ __forceinline__ void bulk_wait_read() {
  asm volatile("cp.async.bulk.commit_group;\ncp.async.bulk.wait_group.read 0;" ::: "memory");
}

__device__ __forceinline__ void publish(void* dst, uint32_t src, uint32_t bytes) {
  bulk_store(dst, src, bytes);
  bulk_wait_read();
}

__device__ __forceinline__ void wg_fence() { asm volatile("wgmma.fence.sync.aligned;" ::: "memory"); }
__device__ __forceinline__ void wg_commit() { asm volatile("wgmma.commit_group.sync.aligned;" ::: "memory"); }
template <int N> __device__ __forceinline__ void wg_wait() { asm volatile("wgmma.wait_group.sync.aligned %0;" ::"n"(N) : "memory"); }
__device__ __forceinline__ uint32_t desc_lo(uint32_t addr, uint32_t lbo) { return ((addr & 0x3FFFF) >> 4) | ((lbo >> 4) << 16); }
constexpr uint32_t desc_hi(uint32_t sbo, uint32_t swz) { return (sbo >> 4) | (swz << 30); }
constexpr uint32_t HI_SW128 = desc_hi(1024, 1), HI_SW64 = desc_hi(512, 2), HI_SW32 = desc_hi(256, 3), HI_NONE = desc_hi(128, 0);
template <int N> __device__ __forceinline__ void pin(float* d) {
#pragma unroll
  for (int i = 0; i < N; i++) asm volatile("" : "+f"(d[i])::"memory");
}

__device__ __forceinline__ uint32_t lds32(uint32_t a) {
  uint32_t v;
  asm volatile("ld.volatile.shared.u32 %0, [%1];" : "=r"(v) : "r"(a) : "memory");
  return v;
}
__device__ __forceinline__ uint2 ldg64(const void* a) {
  uint2 v;
  asm volatile("ld.global.nc.v2.u32 {%0, %1}, [%2];" : "=r"(v.x), "=r"(v.y) : "l"(a) : "memory");
  return v;
}
__device__ __forceinline__ void ldsm4(uint32_t* r, uint32_t a) {
  asm volatile("ldmatrix.sync.aligned.m8n8.x4.shared.b16 {%0, %1, %2, %3}, [%4];"
               : "=r"(r[0]), "=r"(r[1]), "=r"(r[2]), "=r"(r[3]) : "r"(a) : "memory");
}
__device__ __forceinline__ void ldsm4t(uint32_t* r, uint32_t a) {
  asm volatile("ldmatrix.sync.aligned.m8n8.x4.trans.shared.b16 {%0, %1, %2, %3}, [%4];"
               : "=r"(r[0]), "=r"(r[1]), "=r"(r[2]), "=r"(r[3]) : "r"(a) : "memory");
}
__device__ __forceinline__ uint2 lds64(uint32_t a) {
  uint2 v;
  asm volatile("ld.shared.v2.u32 {%0, %1}, [%2];" : "=r"(v.x), "=r"(v.y) : "r"(a) : "memory");
  return v;
}
__device__ __forceinline__ uint4 lds128(uint32_t a) {
  uint4 v;
  asm volatile("ld.shared.v4.u32 {%0, %1, %2, %3}, [%4];" : "=r"(v.x), "=r"(v.y), "=r"(v.z), "=r"(v.w) : "r"(a) : "memory");
  return v;
}
__device__ __forceinline__ void sts128(uint32_t a, uint32_t x, uint32_t y, uint32_t z, uint32_t w) {
  asm volatile("st.shared.v4.u32 [%0], {%1, %2, %3, %4};" ::"r"(a), "r"(x), "r"(y), "r"(z), "r"(w) : "memory");
}
__device__ __forceinline__ void stsm4(uint32_t a, const uint32_t* r) {
  asm volatile("stmatrix.sync.aligned.m8n8.x4.shared.b16 [%0], {%1, %2, %3, %4};" ::"r"(a), "r"(r[0]), "r"(r[1]), "r"(r[2]), "r"(r[3]) : "memory");
}
__device__ __forceinline__ uint32_t pack2(float lo, float hi) {
  uint32_t r;
  asm("cvt.rn.bf16x2.f32 %0, %1, %2;" : "=r"(r) : "f"(hi), "f"(lo));
  return r;
}
__device__ __forceinline__ uint32_t movm(uint32_t a) {
  uint32_t d;
  asm volatile("movmatrix.sync.aligned.m8n8.trans.b16 %0, %1;" : "=r"(d) : "r"(a));
  return d;
}
__device__ __forceinline__ uint32_t bmul(uint32_t a, uint32_t b) {
  uint32_t d;
  asm("mul.rn.bf16x2 %0, %1, %2;" : "=r"(d) : "r"(a), "r"(b));
  return d;
}
__device__ __forceinline__ uint32_t badd(uint32_t a, uint32_t b) {
  uint32_t d;
  asm("add.rn.bf16x2 %0, %1, %2;" : "=r"(d) : "r"(a), "r"(b));
  return d;
}
__device__ __forceinline__ uint32_t bfma(uint32_t a, uint32_t b, uint32_t c) {
  uint32_t d;
  asm("fma.rn.bf16x2 %0, %1, %2, %3;" : "=r"(d) : "r"(a), "r"(b), "r"(c));
  return d;
}
__device__ __forceinline__ float bf_lo(uint32_t x) { return __uint_as_float(x << 16); }
__device__ __forceinline__ float bf_hi(uint32_t x) { return __uint_as_float(x & 0xFFFF0000u); }
__device__ __forceinline__ float ex2(float x) {
  float y;
  asm("ex2.approx.ftz.f32 %0, %1;" : "=f"(y) : "f"(x));
  return y;
}
__device__ __forceinline__ float rcp(float x) {
  float y;
  asm("rcp.approx.ftz.f32 %0, %1;" : "=f"(y) : "f"(x));
  return y;
}
__device__ __forceinline__ void mma16816(float* d, uint32_t a0, uint32_t a1, uint32_t a2, uint32_t a3, uint32_t b0, uint32_t b1) {
  asm volatile("mma.sync.aligned.m16n8k16.row.col.f32.bf16.bf16.f32 {%0, %1, %2, %3}, {%4, %5, %6, %7}, {%8, %9}, {%0, %1, %2, %3};"
               : "+f"(d[0]), "+f"(d[1]), "+f"(d[2]), "+f"(d[3])
               : "r"(a0), "r"(a1), "r"(a2), "r"(a3), "r"(b0), "r"(b1));
}
__device__ __forceinline__ void mma1688(float* d, uint32_t a0, uint32_t a1, uint32_t b0) {
  asm volatile("mma.sync.aligned.m16n8k8.row.col.f32.bf16.bf16.f32 {%0, %1, %2, %3}, {%4, %5}, {%6}, {%0, %1, %2, %3};"
               : "+f"(d[0]), "+f"(d[1]), "+f"(d[2]), "+f"(d[3])
               : "r"(a0), "r"(a1), "r"(b0));
}

template <int N> struct WgRS;
template <int N> struct WgSST;
template <> struct WgRS<32> {
  template <uint32_t HB>
  static __device__ __forceinline__ void mma(float* d, const uint32_t* a, uint32_t db) {
    asm volatile("{\n.reg .pred p;\n.reg .b64 db;\nsetp.ne.b32 p, %22, 0;\n"
      "mov.b64 db, {%20, %21};\n"
      "wgmma.mma_async.sync.aligned.m64n32k16.f32.bf16.bf16 {"
      "%0, %1, %2, %3, %4, %5, %6, %7, %8, %9, %10, %11, %12, %13, %14, %15"
      "}, {%16, %17, %18, %19}, db, p, 1, 1, 1;\n}\n"
      : "+f"(d[0]), "+f"(d[1]), "+f"(d[2]), "+f"(d[3]), "+f"(d[4]), "+f"(d[5]), "+f"(d[6]), "+f"(d[7]),
        "+f"(d[8]), "+f"(d[9]), "+f"(d[10]), "+f"(d[11]), "+f"(d[12]), "+f"(d[13]), "+f"(d[14]), "+f"(d[15])
      : "r"(a[0]), "r"(a[1]), "r"(a[2]), "r"(a[3]), "r"(db), "n"(HB), "n"(1));
  }
  template <uint32_t HB>
  static __device__ __forceinline__ void set(float* d, const uint32_t* a, uint32_t db) {
    asm volatile("{\n.reg .pred p;\n.reg .b64 db;\nsetp.ne.b32 p, %22, 0;\n"
      "mov.b64 db, {%20, %21};\n"
      "wgmma.mma_async.sync.aligned.m64n32k16.f32.bf16.bf16 {"
      "%0, %1, %2, %3, %4, %5, %6, %7, %8, %9, %10, %11, %12, %13, %14, %15"
      "}, {%16, %17, %18, %19}, db, p, 1, 1, 1;\n}\n"
      : "=f"(d[0]), "=f"(d[1]), "=f"(d[2]), "=f"(d[3]), "=f"(d[4]), "=f"(d[5]), "=f"(d[6]), "=f"(d[7]),
        "=f"(d[8]), "=f"(d[9]), "=f"(d[10]), "=f"(d[11]), "=f"(d[12]), "=f"(d[13]), "=f"(d[14]), "=f"(d[15])
      : "r"(a[0]), "r"(a[1]), "r"(a[2]), "r"(a[3]), "r"(db), "n"(HB), "n"(0));
  }
};
template <> struct WgRS<64> {
  template <uint32_t HB>
  static __device__ __forceinline__ void mma(float* d, const uint32_t* a, uint32_t db) {
    asm volatile("{\n.reg .pred p;\n.reg .b64 db;\nsetp.ne.b32 p, %38, 0;\n"
      "mov.b64 db, {%36, %37};\n"
      "wgmma.mma_async.sync.aligned.m64n64k16.f32.bf16.bf16 {"
      "%0, %1, %2, %3, %4, %5, %6, %7, %8, %9, %10, %11, %12, %13, %14, %15, "
      "%16, %17, %18, %19, %20, %21, %22, %23, %24, %25, %26, %27, %28, %29, %30, %31"
      "}, {%32, %33, %34, %35}, db, p, 1, 1, 1;\n}\n"
      : "+f"(d[0]), "+f"(d[1]), "+f"(d[2]), "+f"(d[3]), "+f"(d[4]), "+f"(d[5]), "+f"(d[6]), "+f"(d[7]),
        "+f"(d[8]), "+f"(d[9]), "+f"(d[10]), "+f"(d[11]), "+f"(d[12]), "+f"(d[13]), "+f"(d[14]), "+f"(d[15]),
        "+f"(d[16]), "+f"(d[17]), "+f"(d[18]), "+f"(d[19]), "+f"(d[20]), "+f"(d[21]), "+f"(d[22]), "+f"(d[23]),
        "+f"(d[24]), "+f"(d[25]), "+f"(d[26]), "+f"(d[27]), "+f"(d[28]), "+f"(d[29]), "+f"(d[30]), "+f"(d[31])
      : "r"(a[0]), "r"(a[1]), "r"(a[2]), "r"(a[3]), "r"(db), "n"(HB), "n"(1));
  }
  template <uint32_t HB>
  static __device__ __forceinline__ void set(float* d, const uint32_t* a, uint32_t db) {
    asm volatile("{\n.reg .pred p;\n.reg .b64 db;\nsetp.ne.b32 p, %38, 0;\n"
      "mov.b64 db, {%36, %37};\n"
      "wgmma.mma_async.sync.aligned.m64n64k16.f32.bf16.bf16 {"
      "%0, %1, %2, %3, %4, %5, %6, %7, %8, %9, %10, %11, %12, %13, %14, %15, "
      "%16, %17, %18, %19, %20, %21, %22, %23, %24, %25, %26, %27, %28, %29, %30, %31"
      "}, {%32, %33, %34, %35}, db, p, 1, 1, 1;\n}\n"
      : "=f"(d[0]), "=f"(d[1]), "=f"(d[2]), "=f"(d[3]), "=f"(d[4]), "=f"(d[5]), "=f"(d[6]), "=f"(d[7]),
        "=f"(d[8]), "=f"(d[9]), "=f"(d[10]), "=f"(d[11]), "=f"(d[12]), "=f"(d[13]), "=f"(d[14]), "=f"(d[15]),
        "=f"(d[16]), "=f"(d[17]), "=f"(d[18]), "=f"(d[19]), "=f"(d[20]), "=f"(d[21]), "=f"(d[22]), "=f"(d[23]),
        "=f"(d[24]), "=f"(d[25]), "=f"(d[26]), "=f"(d[27]), "=f"(d[28]), "=f"(d[29]), "=f"(d[30]), "=f"(d[31])
      : "r"(a[0]), "r"(a[1]), "r"(a[2]), "r"(a[3]), "r"(db), "n"(HB), "n"(0));
  }
};
template <> struct WgSST<48> {
  template <uint32_t HA, uint32_t HB>
  static __device__ __forceinline__ void mma(float* d, uint32_t da, uint32_t db, int sc) {
    asm volatile("{\n.reg .pred p;\n.reg .b64 da, db;\nsetp.ne.b32 p, %28, 0;\n"
      "mov.b64 da, {%24, %25};\nmov.b64 db, {%26, %27};\n"
      "wgmma.mma_async.sync.aligned.m64n48k16.f32.bf16.bf16 {"
      "%0, %1, %2, %3, %4, %5, %6, %7, %8, %9, %10, %11, %12, %13, %14, %15, "
      "%16, %17, %18, %19, %20, %21, %22, %23"
      "}, da, db, p, 1, 1, 0, 1;\n}\n"
      : "+f"(d[0]), "+f"(d[1]), "+f"(d[2]), "+f"(d[3]), "+f"(d[4]), "+f"(d[5]), "+f"(d[6]), "+f"(d[7]),
        "+f"(d[8]), "+f"(d[9]), "+f"(d[10]), "+f"(d[11]), "+f"(d[12]), "+f"(d[13]), "+f"(d[14]), "+f"(d[15]),
        "+f"(d[16]), "+f"(d[17]), "+f"(d[18]), "+f"(d[19]), "+f"(d[20]), "+f"(d[21]), "+f"(d[22]), "+f"(d[23])
      : "r"(da), "n"(HA), "r"(db), "n"(HB), "r"(sc));
  }
};
template <> struct WgSST<80> {
  template <uint32_t HA, uint32_t HB>
  static __device__ __forceinline__ void mma(float* d, uint32_t da, uint32_t db, int sc) {
    asm volatile("{\n.reg .pred p;\n.reg .b64 da, db;\nsetp.ne.b32 p, %44, 0;\n"
      "mov.b64 da, {%40, %41};\nmov.b64 db, {%42, %43};\n"
      "wgmma.mma_async.sync.aligned.m64n80k16.f32.bf16.bf16 {"
      "%0, %1, %2, %3, %4, %5, %6, %7, %8, %9, %10, %11, %12, %13, %14, %15, "
      "%16, %17, %18, %19, %20, %21, %22, %23, %24, %25, %26, %27, %28, %29, %30, %31, "
      "%32, %33, %34, %35, %36, %37, %38, %39"
      "}, da, db, p, 1, 1, 0, 1;\n}\n"
      : "+f"(d[0]), "+f"(d[1]), "+f"(d[2]), "+f"(d[3]), "+f"(d[4]), "+f"(d[5]), "+f"(d[6]), "+f"(d[7]),
        "+f"(d[8]), "+f"(d[9]), "+f"(d[10]), "+f"(d[11]), "+f"(d[12]), "+f"(d[13]), "+f"(d[14]), "+f"(d[15]),
        "+f"(d[16]), "+f"(d[17]), "+f"(d[18]), "+f"(d[19]), "+f"(d[20]), "+f"(d[21]), "+f"(d[22]), "+f"(d[23]),
        "+f"(d[24]), "+f"(d[25]), "+f"(d[26]), "+f"(d[27]), "+f"(d[28]), "+f"(d[29]), "+f"(d[30]), "+f"(d[31]),
        "+f"(d[32]), "+f"(d[33]), "+f"(d[34]), "+f"(d[35]), "+f"(d[36]), "+f"(d[37]), "+f"(d[38]), "+f"(d[39])
      : "r"(da), "n"(HA), "r"(db), "n"(HB), "r"(sc));
  }
};
template <> struct WgSST<192> {
  template <uint32_t HA, uint32_t HB>
  static __device__ __forceinline__ void mma(float* d, uint32_t da, uint32_t db, int sc) {
    asm volatile("{\n.reg .pred p;\n.reg .b64 da, db;\nsetp.ne.b32 p, %100, 0;\n"
      "mov.b64 da, {%96, %97};\nmov.b64 db, {%98, %99};\n"
      "wgmma.mma_async.sync.aligned.m64n192k16.f32.bf16.bf16 {"
      "%0, %1, %2, %3, %4, %5, %6, %7, %8, %9, %10, %11, %12, %13, %14, %15, "
      "%16, %17, %18, %19, %20, %21, %22, %23, %24, %25, %26, %27, %28, %29, %30, %31, "
      "%32, %33, %34, %35, %36, %37, %38, %39, %40, %41, %42, %43, %44, %45, %46, %47, "
      "%48, %49, %50, %51, %52, %53, %54, %55, %56, %57, %58, %59, %60, %61, %62, %63, "
      "%64, %65, %66, %67, %68, %69, %70, %71, %72, %73, %74, %75, %76, %77, %78, %79, "
      "%80, %81, %82, %83, %84, %85, %86, %87, %88, %89, %90, %91, %92, %93, %94, %95"
      "}, da, db, p, 1, 1, 0, 1;\n}\n"
      : "+f"(d[0]), "+f"(d[1]), "+f"(d[2]), "+f"(d[3]), "+f"(d[4]), "+f"(d[5]), "+f"(d[6]), "+f"(d[7]),
        "+f"(d[8]), "+f"(d[9]), "+f"(d[10]), "+f"(d[11]), "+f"(d[12]), "+f"(d[13]), "+f"(d[14]), "+f"(d[15]),
        "+f"(d[16]), "+f"(d[17]), "+f"(d[18]), "+f"(d[19]), "+f"(d[20]), "+f"(d[21]), "+f"(d[22]), "+f"(d[23]),
        "+f"(d[24]), "+f"(d[25]), "+f"(d[26]), "+f"(d[27]), "+f"(d[28]), "+f"(d[29]), "+f"(d[30]), "+f"(d[31]),
        "+f"(d[32]), "+f"(d[33]), "+f"(d[34]), "+f"(d[35]), "+f"(d[36]), "+f"(d[37]), "+f"(d[38]), "+f"(d[39]),
        "+f"(d[40]), "+f"(d[41]), "+f"(d[42]), "+f"(d[43]), "+f"(d[44]), "+f"(d[45]), "+f"(d[46]), "+f"(d[47]),
        "+f"(d[48]), "+f"(d[49]), "+f"(d[50]), "+f"(d[51]), "+f"(d[52]), "+f"(d[53]), "+f"(d[54]), "+f"(d[55]),
        "+f"(d[56]), "+f"(d[57]), "+f"(d[58]), "+f"(d[59]), "+f"(d[60]), "+f"(d[61]), "+f"(d[62]), "+f"(d[63]),
        "+f"(d[64]), "+f"(d[65]), "+f"(d[66]), "+f"(d[67]), "+f"(d[68]), "+f"(d[69]), "+f"(d[70]), "+f"(d[71]),
        "+f"(d[72]), "+f"(d[73]), "+f"(d[74]), "+f"(d[75]), "+f"(d[76]), "+f"(d[77]), "+f"(d[78]), "+f"(d[79]),
        "+f"(d[80]), "+f"(d[81]), "+f"(d[82]), "+f"(d[83]), "+f"(d[84]), "+f"(d[85]), "+f"(d[86]), "+f"(d[87]),
        "+f"(d[88]), "+f"(d[89]), "+f"(d[90]), "+f"(d[91]), "+f"(d[92]), "+f"(d[93]), "+f"(d[94]), "+f"(d[95])
      : "r"(da), "n"(HA), "r"(db), "n"(HB), "r"(sc));
  }
};

struct FftConst {
  uint32_t f[2][4], fi[4][4];
  uint32_t ta[2][2], tb[2][2];
};
__device__ __forceinline__ void cis(int m, float scale, float& c, float& s) {
  const float a = (float)m * (-6.283185307179586f * scale);
  c = __cosf(a);
  s = __sinf(a);
}
__device__ __forceinline__ void fft_tables(uint32_t (&v)[12], int tw) {
  const int row = tw >> 2, ch = tw & 3;
#pragma unroll
  for (int i = 0; i < 4; i++) {
    float c[2], s[2], x[2];
#pragma unroll
    for (int e = 0; e < 2; e++) {
      cis((((32 * (8 * ch + 2 * i + e) + 15) * (4 * row - 63) + 2048) & 4095) - 2048, 1.f / 4096, c[e], s[e]);
      float gc, gs;
      cis((((row & 15) * (8 * (ch & 1) + 2 * i + e) + 8) & 15) - 8, 1.f / 16, gc, gs);
      x[e] = (row >> 4) == (ch >> 1) ? gc : (ch >> 1) ? gs : -gs;
    }
    v[i] = pack2(c[0] * 0.125f, c[1] * 0.125f);
    v[4 + i] = pack2(s[0] * 0.125f, s[1] * 0.125f);
    v[8 + i] = pack2(x[0], x[1]);
  }
#pragma unroll
  for (int i = 0; i < 12; i++) asm volatile("" : "+r"(v[i]));
}
__device__ __forceinline__ void fft_tables_store(const uint32_t (&v)[12], uint32_t sb, int tw) {
  const int row = tw >> 2;
  const uint32_t x = ((tw ^ (row >> 1)) & 3) << 4, a = sb + OFF_FT + (16 * (row >> 3) + (row & 7)) * 64 + x;
  sts128(a, v[0], v[1], v[2], v[3]);
  sts128(a + 512, v[4], v[5], v[6], v[7]);
  sts128(sb + OFF_GT + row * 64 + x, v[8], v[9], v[10], v[11]);
}
__device__ __forceinline__ void fft_twiddles(uint32_t (&v)[2], int tw) {
  float a[2], s[2];
#pragma unroll
  for (int i = 0; i < 2; i++) {
    float c;
    cis((2 * (2 * (tw & 3) + i) - 15) * (4 * (tw >> 2) - 63), 1.f / 4096, c, s[i]);
    a[i] = __fdividef(-s[i], 1.f + c);
  }
  v[0] = pack2(a[0], a[1]);
  v[1] = pack2(s[0], s[1]);
  asm volatile("" : "+r"(v[0]), "+r"(v[1]));
}
__device__ __forceinline__ void fft_matrices(FftConst& k, uint32_t sb, int w, int lane) {
  const uint32_t x = (lane >> 1) & 3;
  const uint2 t0 = lds64(sb + OFF_TT + 256 * w + 8 * lane), t1 = lds64(sb + OFF_TT + 256 * w + 8 * (lane ^ 3));
  k.ta[0][0] = t0.x;
  k.tb[0][0] = t0.y;
  k.ta[1][1] = __byte_perm(t1.x, 0, 0x1032);
  k.tb[1][1] = __byte_perm(t1.y, 0, 0x1032);
#pragma unroll
  for (int j = 0; j < 2; j++) {
    k.ta[1 - j][j] = k.ta[j][j] ^ 0x80008000u;
    k.tb[1 - j][j] = k.tb[j][j] ^ 0x80008000u;
    asm volatile("" : "+r"(k.ta[0][j]), "+r"(k.tb[0][j]), "+r"(k.ta[1][j]), "+r"(k.tb[1][j]));
  }
#pragma unroll
  for (int i = 0; i < 2; i++) {
    ldsm4(k.f[i], sb + OFF_FT + (16 * w + (lane & 15)) * 64 + (((2 * i + (lane >> 4)) ^ x) << 4));
    ldsm4t(k.fi[i], sb + OFF_FT + (32 * i + lane) * 64 + ((w ^ x) << 4));
#pragma unroll
    for (int j = 0; j < 4; j++) {
      k.fi[2 + i][j] = (j & 1) ? k.fi[i][j - 1] ^ 0x80008000u : k.fi[i][j + 1];
      asm volatile("" : "+r"(k.fi[2 + i][j]));
    }
  }
}
__device__ __forceinline__ void rot(uint32_t& x, uint32_t& y, uint32_t a, uint32_t b) {
  x = bfma(a, y, x);
  y = bfma(b, x, y);
  x = bfma(a, y, x);
}
__device__ __forceinline__ void twiddle_fwd(uint32_t (&a)[4][4], float* d, const FftConst& k) {
#pragma unroll
  for (int q = 0; q < 4; q++)
#pragma unroll
    for (int j = 0; j < 2; j++) {
      const float* x = d + 8 * q + 4 * j;
      uint32_t re = pack2(x[0], x[1]), im = pack2(x[2], x[3]);
      rot(re, im, k.ta[0][j], k.tb[0][j]);
      a[q & 2][2 * j + (q & 1)] = re;
      a[(q & 2) + 1][2 * j + (q & 1)] = im;
    }
}
__device__ __forceinline__ void g_step(float* d, const uint32_t (&a)[4][4], uint32_t dre, uint32_t dim) {
  WgRS<32>::set<HI_SW64>(d, a[0], dre);
  WgRS<32>::set<HI_SW64>(d + 16, a[2], dre);
  WgRS<32>::mma<HI_SW64>(d, a[1], dim);
  WgRS<32>::mma<HI_SW64>(d + 16, a[3], dim);
  wg_commit();
}

__device__ __forceinline__ void products(uint32_t (&a)[4][4], const float* H, const float* U, int p) {
#pragma unroll
  for (int j = 0; j < 2; j++)
#pragma unroll
    for (int m = 2 * p; m < 2 * p + 2; m++) {
      float pr[2], pi[2];
#pragma unroll
      for (int x = 0; x < 2; x++)
#pragma unroll
        for (int q = 0; q <= m; q++) {
          const int ih = 16 * (q >> 1) + 2 * (q & 1) + 4 * j + x, iu = 16 * ((m - q) >> 1) + 2 * ((m - q) & 1) + 4 * j + x;
          pr[x] = q ? fmaf(H[ih], U[iu], pr[x]) : H[ih] * U[iu];
          pi[x] = q ? fmaf(H[ih], U[iu + 8], pi[x]) : H[ih] * U[iu + 8];
          pr[x] = fmaf(-H[ih + 8], U[iu + 8], pr[x]);
          pi[x] = fmaf(H[ih + 8], U[iu], pi[x]);
        }
      a[m & 2][2 * j + (m & 1)] = pack2(pr[0], pr[1]);
      a[(m & 2) + 1][2 * j + (m & 1)] = pack2(pi[0], pi[1]);
    }
}

__device__ __forceinline__ void conv_channel(const FftConst& k, uint32_t sb, int c, int wg, int w, int lane) {
  const uint32_t cb = sb + off_ch(c), bars = sb + OFF_BAR;
  const uint32_t du = desc_lo(cb, 1024), dg = desc_lo(sb + OFF_GT, 16), dz = desc_lo(cb + U_BYTES, 16);
  float U[32], H[32];
  uint32_t a[4][4], e[4][4];
  const float dv = __uint_as_float(lds32(sb + OFF_D + 4 * c));
  wg_fence();
  WgRS<64>::set<HI_SW32>(H, k.f[0], du + 256);
  WgRS<64>::mma<HI_SW32>(H, k.f[1], du + 256 + 32);
  wg_commit();
  wg_wait<0>();
  pin<32>(H);
  twiddle_fwd(a, H, k);
  mbar_wait(bars + 8 * (B_U + (c < 3 ? c : 3)), 0);
  TSM(w == 0 && c < 3, 7 + wg);
  wg_fence();
  WgRS<64>::set<HI_SW32>(U, k.f[0], du);
  WgRS<64>::mma<HI_SW32>(U, k.f[1], du + 32);
  wg_commit();
  g_step(H, a, dg, dg + 64);
  wg_wait<1>();
  pin<32>(U);
  twiddle_fwd(e, U, k);
  wg_fence();
  g_step(U, e, dg, dg + 64);
  wg_wait<0>();
  pin<32>(U);
  pin<32>(H);
#pragma unroll
  for (int j = 0; j < 4; j++) H[4 * (j >> 1) + (j & 1)] += dv;
  float V[32];
#pragma unroll
  for (int p = 0; p < 2; p++) {
    products(a, H, U, p);
    wg_fence();
    WgRS<32>::set<HI_SW64>(V + 16 * p, a[2 * p], dg + 64);
    WgRS<32>::mma<HI_SW64>(V + 16 * p, a[2 * p + 1], dg);
    wg_commit();
  }
  const uint32_t za = cb + U_BYTES + (8 * w + (lane & 7)) * 128 + (((lane >> 3) ^ (lane & 7)) << 4);
  const uint32_t ya = cb + (lane >> 4) * 1024 + (8 * w + (lane & 7)) * 32 + ((((lane >> 3) ^ (lane >> 2)) & 1) << 4);
  wg_sync(1 + wg);
#pragma unroll
  for (int p = 0; p < 2; p++) {
    if (p == 0) wg_wait<1>();
    else wg_wait<0>();
    pin<16>(V + 16 * p);
#pragma unroll
    for (int i = 0; i < 4; i++) {
      const int j = i & 1;
      const float* x = V + 16 * p + 4 * j + (i & 2);
      e[p][i] = pack2(x[8], x[9]);
      e[2 + p][i] = pack2(x[0], x[1]);
      rot(e[p][i], e[2 + p][i], k.ta[1][j], k.tb[1][j]);
    }
    stsm4(za ^ (64 * p), e[p]);
    stsm4((za ^ (64 * p)) + 4096, e[2 + p]);
  }
  fence_async_smem();
  wg_sync(1 + wg);
  wg_fence();
  WgRS<64>::set<HI_SW128>(H, k.fi[0], dz);
#pragma unroll
  for (int ks = 1; ks < 4; ks++) WgRS<64>::mma<HI_SW128>(H, k.fi[ks], dz + 128 * ks);
  wg_commit();
  wg_wait<0>();
  pin<32>(H);
  if (lane == 0) mbar_arrive(bars + 8 * B_CVD);
  TSIF(w == 0, 88 + c);
#pragma unroll
  for (int j = 0; j < 8; j++)
    a[j >> 2][j & 3] = j < 2 ? pack2(H[4 * j], H[4 * j + 1]) : pack2(H[4 * j] + H[4 * j - 6], H[4 * j + 1] + H[4 * j - 5]);
  stsm4(ya, a[0]);
  stsm4(ya + 2048, a[1]);
  fence_async_smem();
  __syncwarp();
}

__device__ __forceinline__ void prep_slab(uint4* res, const uint2* sw, uint32_t sb, int slab, int w, int lane) {
  const int t = lane & 3, tp = (lane & 7) >> 1, pos = 8 * tp + 2 * (((lane >> 3) + tp) & 3) + (lane & 1);
  const uint32_t base = sb + OFF_KVS + slab * KVS_BYTES + pos * 128;
  uint32_t kk[2][4][4], vv[2][4];
  mbar_wait(sb + OFF_BAR + 8 * (B_KV + slab), 0);
#pragma unroll
  for (int h = 0; h < 2; h++) {
#pragma unroll
    for (int j = 0; j < 4; j++) {
      const uint32_t a = base + 128 * j;
      ldsm4t(kk[h][j], a + (((w + 4 * h) ^ ((a >> 7) & 7)) << 4));
    }
    const uint32_t a = base + KVS_V;
    ldsm4t(vv[h], a + (((w + 4 * h) ^ ((a >> 7) & 7)) << 4));
  }
#pragma unroll
  for (int h = 0; h < 2; h++) {
    uint32_t (&k)[4][4] = kk[h];
    uint32_t (&v)[4] = vv[h];
    const uint32_t w0 = __byte_perm(sw[h].x, 0, 0x1010), w1 = __byte_perm(sw[h].x, 0, 0x3232);
    const uint32_t w2 = __byte_perm(sw[h].y, 0, 0x1010), w3 = __byte_perm(sw[h].y, 0, 0x3232);
#pragma unroll
    for (int m = 0; m < 4; m++)
      v[m] = bmul(badd(badd(badd(bmul(k[0][m], w3), bmul(k[1][m], w2)), bmul(k[2][m], w1)), bmul(k[3][m], w0)), v[m]);
    uint32_t a[4];
#pragma unroll
    for (int m = 0; m < 4; m++) a[m] = (t & 1) ? v[(m + 3) & 3] : v[m];
    res[h] = (t & 2) ? make_uint4(a[2], a[3], a[0], a[1]) : make_uint4(a[0], a[1], a[2], a[3]);
  }
}

__device__ __forceinline__ void prep_gate(const Params& p, uint32_t sb, int b, int w, int lane) {
  uint2 gw[5], x[4][5];
#pragma unroll
  for (int j = 0; j < 5; j++) gw[j] = ldg64(reinterpret_cast<const uint2*>(p.gate_w) + lane + 32 * j);
#pragma unroll
  for (int i = 0; i < 4; i++)
#pragma unroll
    for (int j = 0; j < 5; j++)
      x[i][j] = ldg64(reinterpret_cast<const uint2*>(p.q) + (16 * b + 4 * w + i) * (DIM / 4) + lane + 32 * j);
  float s[4];
#pragma unroll
  for (int i = 0; i < 4; i++) {
    s[i] = 0.f;
#pragma unroll
    for (int j = 0; j < 5; j++) {
      const uint32_t m0 = bmul(x[i][j].x, gw[j].x), m1 = bmul(x[i][j].y, gw[j].y);
      s[i] += (bf_lo(m0) + bf_hi(m0)) + (bf_lo(m1) + bf_hi(m1));
    }
  }
  const bool h = lane & 16, q = lane & 8;
  const float a = (h ? s[2] : s[0]) + __shfl_xor_sync(0xffffffffu, h ? s[0] : s[2], 16);
  const float c = (h ? s[3] : s[1]) + __shfl_xor_sync(0xffffffffu, h ? s[1] : s[3], 16);
  float z = (q ? c : a) + __shfl_xor_sync(0xffffffffu, q ? a : c, 8);
#pragma unroll
  for (int o = 4; o > 0; o >>= 1) z += __shfl_xor_sync(0xffffffffu, z, o);
  z = bf_lo(pack2(z, 0.f));
  z = bf_lo(pack2(__fdividef(1.f, 1.f + __expf(-z)), 0.f));
  mbar_wait(sb + OFF_BAR + 8 * B_S3, 0);
  if ((lane & 7) == 0) asm volatile("st.shared.f32 [%0], %1;" ::"r"(sb + OFF_GATE + 64 * (b & 7) + 16 * w + (lane >> 1)), "f"(z) : "memory");
  fence_async_smem();
}

__device__ __forceinline__ uint32_t bmax(uint32_t a, uint32_t b) {
  uint32_t d;
  asm("max.bf16x2 %0, %1, %2;" : "=r"(d) : "r"(a), "r"(b));
  return d;
}
__device__ __forceinline__ void softmax_two(const float (&l)[2][2], uint32_t& p0, uint32_t& p1) {
  constexpr float kScale = 0.22360679774997896f, kLog2e = 1.4426950408889634f;
  const uint32_t r0 = pack2(l[0][0], l[1][0]), r1 = pack2(l[0][1], l[1][1]);
  const uint32_t x0 = pack2(bf_lo(r0) * kScale, bf_hi(r0) * kScale), x1 = pack2(bf_lo(r1) * kScale, bf_hi(r1) * kScale);
  uint32_t m = bmax(x0, x1);
  m = bmax(m, __shfl_xor_sync(0xffffffffu, m, 1));
  m = bmax(m, __shfl_xor_sync(0xffffffffu, m, 2));
  const float m0 = bf_lo(m) * kLog2e, m1 = bf_hi(m) * kLog2e;
  p0 = pack2(ex2(bf_lo(x0) * kLog2e - m0), ex2(bf_lo(x1) * kLog2e - m0));
  p1 = pack2(ex2(bf_hi(x0) * kLog2e - m1), ex2(bf_hi(x1) * kLog2e - m1));
}

__device__ __forceinline__ void halo_read(uint32_t (&kpv)[10], uint32_t (&vpv)[10], uint32_t (&tg)[7], const uint4* hp) {
#pragma unroll
  for (int j = 0; j < 7; j++) {
    uint32_t x0, x1, x2;
    asm volatile("ld.relaxed.gpu.global.v4.u32 {%0, %1, %2, %3}, [%4];"
                 : "=r"(x0), "=r"(x1), "=r"(x2), "=r"(tg[j]) : "l"(hp + 32 * j) : "memory");
    if (j < 4) kpv[3 * j] = x0; else vpv[3 * j - 10] = x0;
    if (j < 3) kpv[3 * j + 1] = x1; else vpv[3 * j - 9] = x1;
    if (j < 3) kpv[3 * j + 2] = x2; else if (j < 6) vpv[3 * j - 8] = x2;
  }
}

template <int ROT>
__device__ __forceinline__ void pack_qkv(const float* acc, uint32_t (&qlo)[10], uint32_t (&qhi)[10], uint32_t (&klo)[10],
                                         uint32_t (&khi)[10], uint32_t (&vlo)[10], uint32_t (&vhi)[10]) {
#pragma unroll
  for (int j = 0; j < 10; j++) {
    const int x = (j + ROT) % 10, tq = x < 8 ? x : 16 + x, tk = x < 8 ? 8 + x : 18 + x, tv = x < 8 ? 16 + x : 20 + x;
    khi[j] = pack2(acc[4 * tk + 2], acc[4 * tk + 3]);
    vhi[j] = movm(pack2(acc[4 * tv + 2], acc[4 * tv + 3]));
    qlo[j] = pack2(acc[4 * tq], acc[4 * tq + 1]);
    qhi[j] = pack2(acc[4 * tq + 2], acc[4 * tq + 3]);
    klo[j] = pack2(acc[4 * tk], acc[4 * tk + 1]);
    vlo[j] = pack2(acc[4 * tv], acc[4 * tv + 1]);
    asm volatile("" : "+r"(khi[j]), "+r"(qlo[j]), "+r"(qhi[j]), "+r"(klo[j]), "+r"(vlo[j]));
  }
}

template <int ROT> __device__ __forceinline__ void halo_send(const float* acc, uint4* ho, uint32_t tag) {
#pragma unroll
  for (int j = 0; j < 7; j++) {
    uint32_t x[3];
#pragma unroll
    for (int e = 0; e < 3; e++) {
      const int i = 3 * j + e, y = (i % 10 + ROT) % 10, tk = y < 8 ? 8 + y : 18 + y, tv = y < 8 ? 16 + y : 20 + y;
      x[e] = i < 10 ? pack2(acc[4 * tk + 2], acc[4 * tk + 3]) : i < 20 ? movm(pack2(acc[4 * tv + 2], acc[4 * tv + 3])) : 0u;
    }
    asm volatile("st.relaxed.gpu.global.v4.u32 [%0], {%1, %2, %3, %4};" ::"l"(ho + 32 * j), "r"(x[0]), "r"(x[1]), "r"(x[2]), "r"(tag) : "memory");
  }
}

__device__ __forceinline__ void attention(float* acc, uint32_t sb, int b, int par, int w, int lane, uint32_t tag, FftConst& fc) {
  const int g = lane >> 2, t = lane & 3;
  uint32_t klo[10], khi[10], vlo[10], vhi[10], qlo[10], qhi[10], kpv[10], vpv[10];
  if (w == 3 && b < NCTA - 8) {
    uint4* ho = g_halo + (b * 2 + par) * 224 + lane;
    if (tail_first(b & 7)) halo_send<8>(acc, ho, tag);
    else halo_send<0>(acc, ho, tag);
    TSIF(par == 0, 76);
    pin<120>(acc);
  }
  if (tail_first(b & 7)) pack_qkv<8>(acc, qlo, qhi, klo, khi, vlo, vhi);
  else pack_qkv<0>(acc, qlo, qhi, klo, khi, vlo, vhi);
  const uint32_t xa = sb + OFF_KVX + (par * 3) * 2560 + lane * 16;
  if (w < 3) {
    sts128(xa + w * 2560, khi[0], khi[1], khi[2], khi[3]);
    sts128(xa + w * 2560 + 512, khi[4], khi[5], khi[6], khi[7]);
    sts128(xa + w * 2560 + 1024, khi[8], khi[9], vhi[0], vhi[1]);
    sts128(xa + w * 2560 + 1536, vhi[2], vhi[3], vhi[4], vhi[5]);
    sts128(xa + w * 2560 + 2048, vhi[6], vhi[7], vhi[8], vhi[9]);
  }
  TSIF(par == 0 && w == 1, 64);
#pragma unroll
  for (int j = 0; j < 10; j++) vlo[j] = movm(vlo[j]);
  const bool far0 = 2 * t > g, far1 = 2 * t + 1 > g;
  const uint32_t mfar = (far0 ? 0x0000FFFFu : 0u) | (far1 ? 0xFFFF0000u : 0u);
  float slo[4][2], lg[2][2];
  uint32_t phi[4], plo[4], qml[4], qmh[4];
#pragma unroll
  for (int h = 0; h < 4; h++) {
    const int f = h == 0 ? 0 : h == 1 ? 3 : h == 2 ? 5 : 8, hf = h < 2 ? 2 : 7;
    const bool mine = (h & 1) ? t >= 2 : t < 2;
    qml[h] = mine ? qlo[hf] : 0u;
    qmh[h] = mine ? qhi[hf] : 0u;
    float a[4] = {0.f, 0.f, 0.f, 0.f}, c[4] = {0.f, 0.f, 0.f, 0.f};
    mma16816(a, qlo[f], qhi[f], qlo[f + 1], qhi[f + 1], klo[f], klo[f + 1]);
    mma16816(c, qlo[f], qhi[f], qlo[f + 1], qhi[f + 1], khi[f], khi[f + 1]);
    mma1688(a, qml[h], qmh[h], klo[hf]);
    mma1688(c, qml[h], qmh[h], khi[hf]);
    slo[h][0] = a[0];
    slo[h][1] = a[1];
    lg[h & 1][0] = far0 ? a[2] : c[2];
    lg[h & 1][1] = far1 ? a[3] : c[3];
    if (h & 1) softmax_two(lg, phi[h - 1], phi[h]);
  }
  TSIF(par == 0 && w == 1, 65);
  wg_sync(1 + par);
  TSIF(par == 0 && w == 1, 66);
  const bool nohist = (w == 0) && (b < 8);
  const uint4* hp = g_halo + ((b - 8) * 2 + par) * 224 + lane;
  uint32_t tg[7];
  if (w > 0) {
    const uint4 v0 = lds128(xa + (w - 1) * 2560), v1 = lds128(xa + (w - 1) * 2560 + 512), v2 = lds128(xa + (w - 1) * 2560 + 1024);
    const uint4 v3 = lds128(xa + (w - 1) * 2560 + 1536), v4 = lds128(xa + (w - 1) * 2560 + 2048);
    kpv[0] = v0.x; kpv[1] = v0.y; kpv[2] = v0.z; kpv[3] = v0.w; kpv[4] = v1.x; kpv[5] = v1.y; kpv[6] = v1.z; kpv[7] = v1.w;
    kpv[8] = v2.x; kpv[9] = v2.y; vpv[0] = v2.z; vpv[1] = v2.w; vpv[2] = v3.x; vpv[3] = v3.y; vpv[4] = v3.z; vpv[5] = v3.w;
    vpv[6] = v4.x; vpv[7] = v4.y; vpv[8] = v4.z; vpv[9] = v4.w;
  } else if (nohist) {
#pragma unroll
    for (int j = 0; j < 10; j++) kpv[j] = vpv[j] = 0u;
  } else {
    TSIF(par == 0, 77);
    halo_read(kpv, vpv, tg, hp);
  }
  if (w == 0 && !nohist) {
    int spins = 0;
    while (true) {
      bool ok = true;
#pragma unroll
      for (int j = 0; j < 7; j++) ok = ok && tg[j] == tag;
      if (__all_sync(0xffffffffu, ok) || ++spins > SPIN_LIMIT) break;
      halo_read(kpv, vpv, tg, hp);
    }
    TSIF(par == 0, 79);
  }
#pragma unroll
  for (int h = 0; h < 4; h++) {
    const int f = h == 0 ? 0 : h == 1 ? 3 : h == 2 ? 5 : 8, hf = h < 2 ? 2 : 7;
    float a[4] = {0.f, 0.f, 0.f, 0.f};
    mma16816(a, qlo[f], qhi[f], qlo[f + 1], qhi[f + 1], kpv[f], kpv[f + 1]);
    mma1688(a, qml[h], qmh[h], kpv[hf]);
    const float ninf = __int_as_float(0xff800000);
    lg[h & 1][0] = far0 ? (nohist ? ninf : a[0]) : slo[h][0];
    lg[h & 1][1] = far1 ? (nohist ? ninf : a[1]) : slo[h][1];
    if (h & 1) softmax_two(lg, plo[h - 1], plo[h]);
  }
  TSIF(par == 0 && w <= 1, 67 + w);
  mbar_wait(sb + OFF_BAR + 8 * B_HA, 0);
  fft_matrices(fc, sb, w, lane);
  uint32_t ov[20];
#pragma unroll
  for (int hp = 0; hp < 2; hp++) {
    const int hf = hp ? 7 : 2;
    float sh[4] = {0.f, 0.f, 0.f, 0.f}, i0 = 0.f, i1 = 0.f;
#pragma unroll
    for (int e = 0; e < 2; e++) {
      const int h = 2 * hp + e, f = h == 0 ? 0 : h == 1 ? 3 : h == 2 ? 5 : 8;
      const uint32_t a0 = plo[h] & mfar, a2 = plo[h] & ~mfar, a3 = phi[h] & mfar, c1 = phi[h] & ~mfar;
      float sum[4] = {0.f, 0.f, 0.f, 0.f};
      mma1688(sum, plo[h], phi[h], 0x3F803F80u);
      const float r0 = rcp(sum[0]), r1 = rcp(sum[2]);
#pragma unroll
      for (int j = f; j < f + 2; j++) {
        float o[4] = {0.f, 0.f, 0.f, 0.f};
        mma16816(o, a0, 0u, a2, a3, vpv[j], vlo[j]);
        mma1688(o, 0u, c1, vhi[j]);
        ov[2 * j] = pack2(o[0] * r0, o[1] * r0);
        ov[2 * j + 1] = pack2(o[2] * r1, o[3] * r1);
      }
      const bool mine = e ? g >= 4 : g < 4;
      mma16816(sh, a0, 0u, a2, a3, mine ? vpv[hf] : 0u, mine ? vlo[hf] : 0u);
      mma1688(sh, 0u, c1, mine ? vhi[hf] : 0u);
      if (e == 0 || t >= 2) {
        i0 = r0;
        i1 = r1;
      }
    }
    ov[2 * hf] = pack2(sh[0] * i0, sh[1] * i0);
    ov[2 * hf + 1] = pack2(sh[2] * i1, sh[3] * i1);
  }
  TS(32 + 4 * par + w);
  mbar_wait(sb + OFF_BAR + 8 * B_P1, 0);
  const uint32_t oa = sb + OFF_OA + (lane >> 4) * 2048 + (32 * w + 2 * (lane & 15) + par) * 16;
#pragma unroll
  for (int j = 0; j < 5; j++) stsm4(oa + 4096 * j, ov + 4 * j);
  TSIF(par == 0 && w == 0, 120);
  fence_async_smem();
  TSIF(par == 0 && w == 0, 121);
  __syncwarp();
  if (lane == 0) mbar_arrive(sb + OFF_BAR + 8 * B_ATTN);
  TSM(w == 0 || w == 2, 122 + par + (w == 2 ? 3 : 0));
}

struct Maps {
  CUtensorMap x, wm, wt, k, v, y, wo, qm, qt, om, ot, yl, ol, wh;
};

__device__ __forceinline__ void load_stage(uint32_t sb, int kb, int b, const Maps& m) {
  const uint32_t st = sb + (kb & 3) * STAGE_BYTES, bar = sb + OFF_BAR + 8 * (B_FULL1 + (kb & 3));
  const int r = b >> 3, hg = b & 7, slab = kb - KV_KB;
  const bool kv = slab >= 0 && slab < 5;
  const uint32_t kbar = sb + OFF_BAR + 8 * (B_KV + slab), dst = sb + OFF_KVS + slab * KVS_BYTES;
  mbar_expect_tx(bar, STAGE_BYTES);
  if (kv) mbar_expect_tx(kbar, KVS_BYTES);
  tma_3d(st, &m.x, 64 * kb, 64 * r, 0, bar);
  tma_3d(st + ST_W, &m.wm, 80 * hg + (tail_first(hg) ? 16 : 0), 64 * kb, 0, bar);
  tma_3d(st + ST_WT, &m.wt, 80 * hg + (tail_first(hg) ? 0 : 64), 64 * kb, 0, bar);
  if (kv) tma_3d(dst, &m.k, 0, 32 * (b >> 1) - 3, 2 * slab + (b & 1), kbar);
  if (kv) tma_3d(dst + KVS_V, &m.v, 0, 32 * (b >> 1), 2 * slab + (b & 1), kbar);
}

__global__ void __launch_bounds__(NTHR, 1) fused_kernel(const __grid_constant__ Maps m, const Params p) {
  extern __shared__ __align__(1024) uint8_t smem[];
  const uint32_t sb = (uint32_t)__cvta_generic_to_shared(smem);
  const uint32_t bars = sb + OFF_BAR;
  const int tid = threadIdx.x, lane = tid & 31;
  int b = blockIdx.x;
  b = (((b & 63) >> 3) * 2 + (b & 1)) * 8 + (((b < 64 ? 0x6521 : 0x7430) >> (4 * ((b >> 1) & 3))) & 7);
  const int r = b >> 3, hg = b & 7;

  if (tid == T_ISSUE) {
    TSM(true, 0);
#pragma unroll
    for (int i = 0; i < 4; i++) mbar_init(bars + 8 * (B_F0 + i), 1);
    fence_async_smem();
#pragma unroll
    for (int i = 0; i < 4; i++) {
      mbar_expect_tx(bars + 8 * (B_F0 + i), (i ? 0 : ST_W) + 6144);
      if (i == 0) tma_3d(sb, &m.x, 0, 64 * r, 0, bars + 8 * B_F0);
      tma_3d(sb + ST_W + 6144 * i, &m.wh, 80 * hg + (tail_first(hg) ? 16 : 0), 16 * i, 0, bars + 8 * (B_F0 + i));
    }
#pragma unroll
    for (int i = 0; i < 4; i++) mbar_init(bars + 8 * (B_FULL1 + i), 1);
    fence_async_smem();
    mbar_expect_tx(bars + 8 * B_FULL1, STAGE_BYTES - ST_WT);
    tma_3d(sb + ST_WT, &m.wt, 80 * hg + (tail_first(hg) ? 0 : 64), 0, 0, bars + 8 * B_FULL1);
    load_stage(sb, 1, b, m);
  } else if (tid == T_INIT) {
#pragma unroll
    for (int i = 0; i < B_F0; i++) mbar_init(bars + 8 * i, i < B_GATE ? 8 : i < B_CVD ? 4 : i == B_CVD ? 20 : 1);
    fence_async_smem();
  }
  const int warp = __shfl_sync(0xffffffffu, tid >> 5, 0), wg = warp >> 2, w = warp & 3;
  __syncthreads();

  if (wg == 3) {
    asm volatile("setmaxnreg.dec.sync.aligned.u32 56;");
    if (w == 0) {
      if (lane == 0) {
#pragma unroll 1
        for (int kb = 2; kb < 10; kb++) {
          if (kb >= 4) mbar_wait(bars + 8 * (kb == 7 ? B_E3 : B_EMPTY1 + (kb & 3)), (kb >> 3) & 1);
          TSIF(kb >= 4, 44 + kb);
          load_stage(sb, kb, b, m);
          TSIF(kb == 3, 60);
          if (kb == 9) mbar_arrive(bars + 8 * B_LAST);
        }
        mbar_wait(bars + 8 * B_WOP, 0);
        mbar_wait(bars + 8 * B_EPOCH, 0);
        flag_wait(g_cnt + C_W + 32 * hg, (lds32(sb + OFF_EPOCH) + 1) * 16);
        TS(30);
#pragma unroll 1
        for (int j = 0; j < 8; j++) {
          if (j >= 6) mbar_wait(bars + 8 * (B_EMPTY2 + j - 6), 0);
          if (j == 4) mbar_wait(bars + 8 * B_ORB, 0);
          TSIF(j >= 6, 100 + j);
          mbar_expect_tx(bars + 8 * (B_FULL2 + j), j == 0 ? WO_BYTES : j == 5 ? O_BYTES + WO_BYTES + 512 : O_BYTES + WO_BYTES);
          bulk_load(sb + off_w(j), g_WO + (hg * 8 + step_src(hg, j)) * 800, WO_BYTES, bars + 8 * (B_FULL2 + j));
        }
        mbar_wait(bars + 8 * (B_EMPTY2 + 3), 0);
        mbar_expect_tx(bars + 8 * B_QF, O_BYTES);
        tma_2d(sb + OFF_QS, &m.qm, 80 * hg, 128 * r, bars + 8 * B_QF);
        tma_2d(sb + OFF_QT, &m.qt, 80 * hg + 64, 128 * r, bars + 8 * B_QF);
      }
    } else if (w == 1) {
      unsigned epoch = 0;
      if (lane == 0) {
        epoch = atomicAdd(g_cnt + C_LAUNCH, 1u) / NCTA;
        asm volatile("st.shared.u32 [%0], %1;" ::"r"(sb + OFF_EPOCH), "r"(epoch) : "memory");
        mbar_arrive(bars + 8 * B_EPOCH);
        mbar_wait(bars + 8 * B_KVD, 0);
        mbar_expect_tx(bars + 8 * B_HB, 5 * 4096);
#pragma unroll 1
        for (int c = 0; c < 5; c++) {
          if (c == 3) mbar_wait(bars + 8 * B_S3, 0);
          bulk_load(sb + off_ch(c) + U_BYTES, p.ssm_k + (5 * b + c) * SEQ, 4096, bars + 8 * B_HB);
        }
#pragma unroll
        for (int c = 0; c < 4; c++) mbar_expect_tx(bars + 8 * (B_U + c), c < 3 ? U_BYTES : 2 * U_BYTES);
        const uint4* usrc = g_U + 5 * b * U_PITCH;
        mbar_wait(bars + 8 * B_USIG, 0);
        flag_wait(g_cnt + C_PREP + 32 * (b & 15), (epoch + 1) * NCTA);
        TS(23);
#pragma unroll
        for (int c = 0; c < 5; c++) {
          if (c == 3) mbar_wait(bars + 8 * (B_U + 2), 0);
          bulk_load(sb + off_ch(c), usrc + c * U_PITCH, U_BYTES, bars + 8 * (B_U + (c < 3 ? c : 3)));
          TSIF(c == 0 || c == 4, 116 + (c >> 2));
        }
      }
      epoch = __shfl_sync(0xffffffffu, epoch, 0);
      if (lane < 8) {
        const int src = (b & ~7) | step_src(hg, lane);
        mbar_wait(bars + 8 * B_ATTN, 0);
        TS(20);
        bool seen = false;
#pragma unroll 1
        for (int spins = 0; spins < SPIN_LIMIT; spins++) {
          const bool now = !seen && (int)(flag_read(g_cnt + C_O + 32 * src) - (epoch + 1)) >= 0;
          if (now && lane >= 1 && lane < 4) bulk_load(sb + off_o(lane), g_O + src * 1280, O_BYTES, bars + 8 * (B_FULL2 + lane));
          seen = seen || now;
          if (__all_sync(0xff, seen)) break;
        }
        TS(21);
        if (lane == 5) bulk_load(sb + OFF_GATE, g_gate + 128 * r, 512, bars + 8 * (B_FULL2 + 5));
#pragma unroll 1
        for (int j = 4; j < 8; j++) {
          if (lane == j) {
            mbar_wait(bars + 8 * (j < 6 ? B_C34 : B_EMPTY2 + j - 6), 0);
            bulk_load(sb + off_o(j), g_O + src * 1280, O_BYTES, bars + 8 * (B_FULL2 + j));
          }
          __syncwarp(0xff);
        }
        TS(22);
      }
    } else if (w == 2) {
      mbar_wait(bars + 8 * B_PREP, 0);
      flag_signal(g_cnt + C_PREP, 16, lane);
      TS(25);
      if (lane == 0) {
        mbar_arrive(bars + 8 * B_USIG);
        mbar_expect_tx(bars + 8 * B_ORB, O_BYTES / 4 + 64);
        mbar_wait(bars + 8 * B_GATE, 0);
        publish(g_gate + 16 * b, sb + OFF_GATE + 64 * hg, 64);
        bulk_load(sb + OFF_GATE + 64 * hg, g_gate + 16 * b, 64, bars + 8 * B_ORB);
        mbar_wait(bars + 8 * B_ATTN, 0);
        publish(g_O + b * 1280, sb + OFF_OA, O_BYTES);
        tma_2d(sb + OFF_KVX + 10240, &m.ol, 48, b * 160, bars + 8 * B_ORB);
        TS(74);
        mbar_wait(bars + 8 * B_ORB, 0);
        flag_bump(g_cnt + C_O + 32 * b);
        TS(26);
      }
    } else {
      if (lane == 0) {
        uint4* dst = g_WO + (hg * 8 + (r >> 1)) * 800 + (r & 1) * 80;
        mbar_wait(bars + 8 * B_S3, 0);
        asm volatile("cp.async.bulk.prefetch.L2.global [%0], 6400;" ::"l"(p.wo + b * 3200) : "memory");
        mbar_wait(bars + 8 * B_P1, 0);
        mbar_wait(bars + 8 * WB_TRIG, 0);
        mbar_expect_tx(bars + 8 * B_WST, WO_BYTES / 2);
        tma_3d(sb + OFF_WA, &m.wo, 0, 40 * r, 5 * hg, bars + 8 * B_WST);
        mbar_wait(bars + 8 * B_WST, 0);
#pragma unroll 1
        for (int n = 0; n < 5; n++) bulk_store(dst + 160 * n, sb + OFF_WA + 1280 * n, 1280);
        bulk_wait_read();
        mbar_expect_tx(bars + 8 * B_WST, WO_BYTES / 2);
#pragma unroll 1
        for (int n = 0; n < 5; n++) bulk_load(sb + OFF_WA + 1280 * n, dst + 160 * n, 1280, bars + 8 * B_WST);
        mbar_wait(bars + 8 * B_WST, 1);
        flag_bump(g_cnt + C_W + 32 * hg);
        mbar_arrive(bars + 8 * B_WOP);
        TS(71);
        mbar_expect_tx(bars + 8 * B_C34, 3 * (U_BYTES / 4));
        mbar_expect_tx(bars + 8 * B_YRB, 2 * (U_BYTES / 4));
#pragma unroll 1
        for (int c = 0; c < 5; c++) {
          mbar_wait(bars + 8 * (B_YST + c), 0);
          publish(g_U + (5 * b + c) * U_PITCH, sb + off_ch(c), U_BYTES);
          tma_2d(sb + off_ch(c), &m.yl, 48, (5 * b + c) * (U_PITCH / 8), bars + 8 * (c < 3 ? B_C34 : B_YRB));
        }
        TS(75);
        mbar_wait(bars + 8 * B_C34, 0);
        mbar_wait(bars + 8 * B_YRB, 0);
        flag_bump(g_cnt + C_Y + 32 * (b >> 4));
        TS(27);
        mbar_expect_tx(bars + 8 * B_YFULL, 20480);
        flag_wait(g_cnt + C_Y + 32 * hg, (lds32(sb + OFF_EPOCH) + 1) * 16);
        TS(24);
        tma_2d(sb + OFF_YT, &m.y, 128 * r, 80 * hg, bars + 8 * B_YFULL);
        tma_2d(sb + OFF_YT + 10240, &m.y, 128 * r + 64, 80 * hg, bars + 8 * B_YFULL);
      }
    }
  } else {
    asm volatile("setmaxnreg.inc.sync.aligned.u32 152;");
    FftConst fc;
    if (wg < 2) {
      float acc[120];
#pragma unroll
      for (int i = 0; i < 120; i++) acc[i] = 0.f;
      const uint32_t da = desc_lo(sb + wg * 8192, 16), db = desc_lo(sb + ST_W, 8192), dc = desc_lo(sb + ST_WT, 2048);
#pragma unroll
      for (int k = 0; k < 4; k++) {
        mbar_wait(bars + 8 * (B_F0 + k), 0);
        TSIF(w == 0 && wg == 0 && k == 0, 1);
        wg_fence();
        WgSST<192>::mma<HI_SW128, HI_SW128>(acc, da + 2 * k, desc_lo(sb + ST_W, 2048) + 384 * k, 1);
        wg_commit();
      }
      mbar_wait(bars + 8 * B_FULL1, 0);
      wg_fence();
#pragma unroll
      for (int k = 0; k < 4; k++) WgSST<48>::mma<HI_SW128, HI_SW32>(acc + 96, da + 2 * k, dc + 32 * k, 1);
      wg_commit();
#pragma unroll 1
      for (int kb = 1; kb < 10; kb++) {
        mbar_wait(bars + 8 * (B_FULL1 + (kb & 3)), (kb >> 2) & 1);
        const uint32_t so = (kb & 3) * (STAGE_BYTES >> 4);
        wg_fence();
#pragma unroll
        for (int k = 0; k < 4; k++) {
          WgSST<192>::mma<HI_SW128, HI_SW128>(acc, da + so + 2 * k, db + so + 128 * k, 1);
          WgSST<48>::mma<HI_SW128, HI_SW32>(acc + 96, da + so + 2 * k, dc + so + 32 * k, 1);
        }
        wg_commit();
        wg_wait<1>();
        if (lane == 0) mbar_arrive(bars + 8 * (kb == 4 ? B_E3 : B_EMPTY1 + ((kb - 1) & 3)));
      }
      mbar_wait(bars + 8 * B_EPOCH, 0);
      const uint32_t tag = lds32(sb + OFF_EPOCH) + 1;
      mbar_wait(bars + 8 * B_S3, 0);
      wg_wait<0>();
      pin<120>(acc);
      if (lane == 0) mbar_arrive(bars + 8 * B_P1);
      TSM(w == 0, 3 + wg);
      attention(acc, sb, b, wg, w, lane, tag, fc);
    } else {
      const int tw = tid & 127, chl = 64 * (b & 1) + 8 * w + (lane >> 2);
      uint4* up = g_U + chl * U_PITCH + ((4 * (b >> 1) + (lane & 3)) ^ ((b >> 2) & 1));
      uint2 sw[10];
      uint32_t dv = 0;
      if (lane < 5) dv = __ldg(reinterpret_cast<const unsigned short*>(p.ssm_D) + 5 * b + lane);
#pragma unroll
      for (int i = 0; i < 10; i++) sw[i] = ldg64(reinterpret_cast<const uint2*>(p.shift_k) + chl + 128 * (i >> 1) + 32 * (i & 1));
      uint32_t tab[12];
      uint32_t tt[2];
      fft_tables(tab, tw);
      fft_twiddles(tt, tw);
      uint4 res[10];
#pragma unroll
      for (int i = 0; i < 10; i++) res[i] = make_uint4(0, 0, 0, 0);
#pragma unroll 1
      for (int slab = 0; slab < 5; slab++) {
#pragma unroll
        for (int i = 0; i < 8; i++) res[i] = res[i + 2];
        prep_slab(res + 8, sw, sb, slab, w, lane);
        TSIF(w == 0, 99 + 4 * slab);
#pragma unroll
        for (int i = 0; i < 8; i++) sw[i] = sw[i + 2];
      }
      TSIF(w == 0, 28);
      __syncwarp();
      if (lane == 0) mbar_arrive(bars + 8 * B_KVD + ((res[8].x ^ res[9].x) & p.zero));
      mbar_wait(bars + 8 * B_KVD, 0);
      fft_tables_store(tab, sb, tw);
      mbar_wait(bars + 8 * B_LAST, 0);
#pragma unroll
      for (int i = 0; i < 10; i++) up[(128 * (i >> 1) + 32 * (i & 1)) * U_PITCH] = res[i];
      __syncwarp();
      if (lane == 0) mbar_arrive(bars + 8 * B_PREP);
      TSIF(w == 0, 5);
      mbar_wait(bars + 8 * B_LAST, 0);
      prep_gate(p, sb, b, w, lane);
      __syncwarp();
      if (lane == 0) mbar_arrive(bars + 8 * B_GATE);
      TSIF(w == 0, 72);
      mbar_wait(bars + 8 * B_HB, 0);
      TSIF(w == 0, 2);
      const uint32_t ha = sb + U_BYTES + ((tw >> 3) * 16 + 8 + (tw & 7)) * 16;
      uint4 hv[5];
#pragma unroll
      for (int c = 0; c < 5; c++) hv[c] = lds128(ha + off_ch(c));
      __syncwarp();
#pragma unroll
      for (int c = 0; c < 5; c++) sts128((ha ^ 16) + off_ch(c), hv[c].x, hv[c].y, hv[c].z, hv[c].w);
      asm volatile("st.shared.v2.u32 [%0], {%1, %2};" ::"r"(sb + OFF_TT + 8 * tw), "r"(tt[0]), "r"(tt[1]) : "memory");
      if (tw < 5) asm volatile("st.shared.f32 [%0], %1;" ::"r"(sb + OFF_D + 4 * tw), "f"(bf_lo(dv) * 0.125f) : "memory");
      fence_async_smem();
      __syncwarp();
      if (lane == 0) mbar_arrive(bars + 8 * B_HA);
      TSIF(w == 0, 6);
      mbar_wait(bars + 8 * B_HA, 0);
      fft_matrices(fc, sb, w, lane);
    }

    TSM(w == 0 && wg == 2, 124);
#pragma unroll 1
    for (uint32_t tasks = wg == 0 ? TASK0 : wg == 1 ? TASK1 : TASK2; tasks; tasks >>= 4) {
      const int c = (tasks & 7) - 1;
      conv_channel(fc, sb, c, wg, w, lane);
      if (lane == 0) mbar_arrive(bars + 8 * (B_YST + c));
      TSM(w == 0, 10 + c);
    }

    if (wg != 1) {
      const int wg = warp >> 3;
      const int g = lane >> 2;
      float acc[40];
#pragma unroll
      for (int i = 0; i < 40; i++) acc[i] = 0.f;
      const uint32_t da = desc_lo(sb + wg * 1024, 2048), db = desc_lo(sb, 2560);
      mbar_wait(bars + 8 * B_ORB, 0);
      mbar_wait(bars + 8 * B_FULL2, 0);
      TSM(w == 0, 15 + wg);
#pragma unroll 1
      for (int j = 0; j < 8; j++) {
        if (j == 1 - wg) mbar_wait(bars + 8 * B_CVD, 0);
        mbar_wait(bars + 8 * (B_FULL2 + j), 0);
        TSM(w == 0 && wg == 0, 44 + (j < 4 ? j : j + 6));
        const uint32_t oa = da + (off_o(j) >> 4), ob = db + (off_w(j) >> 4);
        wg_fence();
#pragma unroll
        for (int k = 0; k < 5; k++) WgSST<80>::mma<HI_NONE, HI_SW32>(acc, oa + 256 * k, ob + 32 * k, 1);
        wg_commit();
        wg_wait<1>();
        if (j >= 1 && j <= 4 && lane == 0) mbar_arrive(bars + 8 * (B_EMPTY2 + j - 1));
      }
      TSIF(w == 0 && wg == 0, 113);
      const int tr = 64 * wg + 16 * w + (lane & 15);
      const uint32_t fm = sb + OFF_QS + tr * 128, fx = (lane >> 4) ^ (tr & 7);
      const uint32_t ft = sb + OFF_QT + tr * 32 + (((lane >> 4) ^ (tr >> 2)) & 1) * 16;
      const float g0 = __uint_as_float(lds32(sb + OFF_GATE + (64 * wg + 16 * w + g) * 4));
      const float g1 = __uint_as_float(lds32(sb + OFF_GATE + (64 * wg + 16 * w + 8 + g) * 4));
      const uint32_t ga = pack2(g0, g0), gb = pack2(g1, g1);
      const uint32_t na = pack2(1.f - g0, 1.f - g0), nb = pack2(1.f - g1, 1.f - g1);

      uint32_t qf[20];
      mbar_wait(bars + 8 * B_QF, 0);
      TSM(w == 0 && wg == 0, 99);
#pragma unroll
      for (int j = 0; j < 5; j++) ldsm4(qf + 4 * j, j < 4 ? fm + ((fx ^ (2 * j)) << 4) : ft);
#pragma unroll
      for (int i = 0; i < 20; i++) {
        qf[i] = bmul((i & 1) ? gb : ga, qf[i]);
        asm volatile("" : "+r"(qf[i]));
      }

      wg_wait<0>();
      pin<40>(acc);
      TSM(w == 0, 17 + wg);
      uint32_t pb[20];
#pragma unroll
      for (int j = 0; j < 10; j++) {
        pb[2 * j] = bmul(na, pack2(acc[4 * j], acc[4 * j + 1]));
        pb[2 * j + 1] = bmul(nb, pack2(acc[4 * j + 2], acc[4 * j + 3]));
        asm volatile("" : "+r"(pb[2 * j]), "+r"(pb[2 * j + 1]));
      }
      const uint32_t ya = sb + OFF_YT + wg * 10240 + ((lane >> 4) * 8 + (lane & 7)) * 128 +
                          (((2 * w + (((lane >> 3) & 1) ^ wg)) ^ (lane & 7)) << 4);
      mbar_wait(bars + 8 * B_YFULL, 0);
      TSM(w == 0 && wg == 0, 19);
#pragma unroll
      for (int j = 0; j < 5; j++) {
        uint32_t y[4];
        ldsm4t(y, ya + 2048 * j);
#pragma unroll
        for (int i = 0; i < 4; i++)
          qf[4 * j + i] = bfma(qf[4 * j + i], y[i], pb[4 * j + i]);
      }
#pragma unroll
      for (int j = 0; j < 5; j++) stsm4(j < 4 ? fm + ((fx ^ (2 * j)) << 4) : ft, qf + 4 * j);
      fence_async_smem();
      __syncwarp();
      if (lane == 0) {
        const int row = 64 * wg + 16 * w;
        asm volatile("cp.async.bulk.tensor.2d.global.shared::cta.bulk_group [%0, {%2, %3}], [%1];"
                     ::"l"(&m.om), "r"(sb + OFF_QS + row * 128), "r"(80 * hg), "r"(128 * r + row) : "memory");
        asm volatile("cp.async.bulk.tensor.2d.global.shared::cta.bulk_group [%0, {%2, %3}], [%1];"
                     ::"l"(&m.ot), "r"(sb + OFF_QT + row * 32), "r"(80 * hg + 64), "r"(128 * r + row) : "memory");
        asm volatile("cp.async.bulk.commit_group;\ncp.async.bulk.wait_group.read 0;" ::: "memory");
      }
      TSM(w == 0 || w == 3, 40 + 2 * wg + (w & 1));
    }
  }
}

typedef CUresult (*EncodeFn)(CUtensorMap*, CUtensorMapDataType, cuuint32_t, void*, const cuuint64_t*, const cuuint64_t*,
                             const cuuint32_t*, const cuuint32_t*, CUtensorMapInterleave, CUtensorMapSwizzle,
                             CUtensorMapL2promotion, CUtensorMapFloatOOBfill);

void encode(EncodeFn fn, CUtensorMap* tm, const void* base, int rank, const cuuint64_t* dims, const cuuint64_t* strides,
            const cuuint32_t* box, CUtensorMapSwizzle swz) {
  const cuuint32_t ones[3] = {1, 1, 1};
  fn(tm, CU_TENSOR_MAP_DATA_TYPE_BFLOAT16, rank, const_cast<void*>(base), dims, strides, box, ones,
     CU_TENSOR_MAP_INTERLEAVE_NONE, swz, CU_TENSOR_MAP_L2_PROMOTION_L2_128B, CU_TENSOR_MAP_FLOAT_OOB_FILL_NONE);
}

}

extern "C" void kernel_launch(void* const* d_in, const int* in_sizes, int n_in, void* d_out, int out_size) {
  (void)in_sizes; (void)n_in; (void)out_size;
  Params p;
  p.q = (const __nv_bfloat16*)d_in[0];
  p.k = (const __nv_bfloat16*)d_in[1];
  p.v = (const __nv_bfloat16*)d_in[2];
  p.shift_k = (const __nv_bfloat16*)d_in[3];
  p.ssm_k = (const __nv_bfloat16*)d_in[4];
  p.ssm_D = (const __nv_bfloat16*)d_in[5];
  p.wqkv = (const __nv_bfloat16*)d_in[7];
  p.wo = (const __nv_bfloat16*)d_in[8];
  p.gate_w = (const __nv_bfloat16*)d_in[9];
  p.out = (__nv_bfloat16*)d_out;
  p.zero = 0;

  static EncodeFn fn = nullptr;
  static void *yaddr = nullptr, *oaddr = nullptr;
  if (!fn) {
    cudaDriverEntryPointQueryResult qr;
    void* f = nullptr;
    cudaGetDriverEntryPoint("cuTensorMapEncodeTiled", &f, cudaEnableDefault, &qr);
    fn = (EncodeFn)f;
    cudaGetSymbolAddress(&yaddr, g_U);
    cudaGetSymbolAddress(&oaddr, g_O);
    cudaFuncSetAttribute(fused_kernel, cudaFuncAttributeMaxDynamicSharedMemorySize, SMEM_BYTES);
  }
  Maps m;
  {
    const cuuint64_t dims[3] = {640, 1024, 2}, st[2] = {2560, 1280};
    const cuuint32_t box[3] = {64, 64, 2};
    encode(fn, &m.x, p.q, 3, dims, st, box, CU_TENSOR_MAP_SWIZZLE_128B);
  }
  {
    const cuuint64_t dims[3] = {640, 640, 3}, st[2] = {3840, 1280};
    const cuuint32_t box[3] = {64, 64, 3}, boxt[3] = {16, 64, 3};
    encode(fn, &m.wm, p.wqkv, 3, dims, st, box, CU_TENSOR_MAP_SWIZZLE_128B);
    encode(fn, &m.wt, p.wqkv, 3, dims, st, boxt, CU_TENSOR_MAP_SWIZZLE_32B);
    const cuuint32_t boxh[3] = {64, 16, 3};
    encode(fn, &m.wh, p.wqkv, 3, dims, st, boxh, CU_TENSOR_MAP_SWIZZLE_128B);
  }
  {
    const cuuint64_t dims[3] = {64, 2048, 10}, st[2] = {1280, 128};
    const cuuint32_t boxk[3] = {64, 35, 1}, boxv[3] = {64, 32, 1};
    encode(fn, &m.k, p.k, 3, dims, st, boxk, CU_TENSOR_MAP_SWIZZLE_128B);
    encode(fn, &m.v, p.v, 3, dims, st, boxv, CU_TENSOR_MAP_SWIZZLE_128B);
  }
  {
    const cuuint64_t dims[3] = {16, 640, 40}, st[2] = {1280, 32};
    const cuuint32_t box[3] = {16, 40, 5};
    encode(fn, &m.wo, p.wo, 3, dims, st, box, CU_TENSOR_MAP_SWIZZLE_32B);
  }
  {
    const cuuint64_t dims[2] = {2048, 640}, st[1] = {U_PITCH * 16};
    const cuuint32_t box[2] = {64, 80};
    encode(fn, &m.y, yaddr, 2, dims, st, box, CU_TENSOR_MAP_SWIZZLE_128B);
    const cuuint64_t dl[2] = {64, DIM * U_PITCH / 8}, dol[2] = {64, NCTA * 160}, sl[1] = {128};
    const cuuint32_t bl[2] = {16, 32}, bol[2] = {16, 160};
    encode(fn, &m.yl, yaddr, 2, dl, sl, bl, CU_TENSOR_MAP_SWIZZLE_NONE);
    encode(fn, &m.ol, oaddr, 2, dol, sl, bol, CU_TENSOR_MAP_SWIZZLE_NONE);
  }
  {
    const cuuint64_t dims[2] = {640, 2048}, st[1] = {1280};
    const cuuint32_t bqm[2] = {64, 128}, bqt[2] = {16, 128}, bom[2] = {64, 16}, bot[2] = {16, 16};
    encode(fn, &m.qm, p.q, 2, dims, st, bqm, CU_TENSOR_MAP_SWIZZLE_128B);
    encode(fn, &m.qt, p.q, 2, dims, st, bqt, CU_TENSOR_MAP_SWIZZLE_32B);
    encode(fn, &m.om, p.out, 2, dims, st, bom, CU_TENSOR_MAP_SWIZZLE_128B);
    encode(fn, &m.ot, p.out, 2, dims, st, bot, CU_TENSOR_MAP_SWIZZLE_32B);
  }
  fused_kernel<<<NCTA, NTHR, SMEM_BYTES>>>(m, p);
}
```

```cpp
#include <cuda.h>
#include <cuda_bf16.h>
#include <cuda_runtime.h>
#include <stdint.h>

namespace {

constexpr int SEQ = 2048, DIM = 640, NCTA = 128, NTHR = 512;

#define KV_KB 2
#define DEV_EXIT 0
#define FENCE_LO 0
#define FENCE_HI 0
#define WB_TRIG B_USIG
#define T_ISSUE 288
#define PR_X 2
#define PR_W 2
#define PR_T 2
#define PR_K 2
#define PR_R 2
#define T_INIT 448
#define TASK0 0x3
#define TASK1 0x52
#define TASK2 0x41

constexpr uint32_t STAGE_BYTES = 47104, ST_W = 16384, ST_WT = 40960;
constexpr uint32_t O_BYTES = 20480, WO_BYTES = 12800;
constexpr uint32_t OFF_OA = 0;
constexpr uint32_t OFF_QS = 3 * O_BYTES, OFF_QT = OFF_QS + 16384;
constexpr uint32_t OFF_WC = 81920;
constexpr uint32_t OFF_WA = 94720;
constexpr uint32_t OFF_GATE = 145920;
constexpr uint32_t OFF_TT = 146432;
constexpr uint32_t OFF_KVX = 148480;
constexpr uint32_t OFF_CH3 = 163840;
constexpr uint32_t CH_BYTES = 12288, U_BYTES = 4096;
constexpr uint32_t OFF_FT = 225280, OFF_GT = 229376;
constexpr uint32_t OFF_CH0 = 188416;
constexpr uint32_t OFF_KVS = OFF_CH0, KVS_V = 4480, KVS_BYTES = 8576;
constexpr uint32_t OFF_YT = 163840;
constexpr uint32_t OFF_BAR = 231936;
constexpr uint32_t SMEM_BYTES = OFF_BAR + 512;

enum : uint32_t {
  B_EMPTY1 = 0, B_S3 = 3, B_E3 = 4, B_EMPTY2 = 5, B_ATTN = 9, B_P1 = 10,
  B_GATE = 11, B_HA = 12, B_KVD = 13, B_PREP = 14, B_YST = 15,
  B_CVD = 20,
  B_FULL2 = 21, B_U = 29, B_KV = 33, B_HB = 38, B_C34 = 39, B_YRB = 40, B_YFULL = 41, B_EPOCH = 42, B_LAST = 43,
  B_WOP = 44, B_USIG = 45, B_WST = 46, B_QF = 47, B_ORB = 48,
  B_F0 = 49, B_FULL1 = 53
};
constexpr uint32_t OFF_EPOCH = OFF_BAR + 8 * 58, OFF_D = OFF_BAR + 8 * 60;
__device__ __forceinline__ uint32_t off_o(int j) { return j < 4 ? OFF_OA + j * O_BYTES : j < 6 ? OFF_CH0 + (j - 4) * O_BYTES : OFF_OA + (j - 6) * O_BYTES; }
__device__ __forceinline__ uint32_t off_w(int j) { return j < 4 ? OFF_WA + j * WO_BYTES : j == 4 ? OFF_KVX : j == 5 ? OFF_WC : OFF_WA + (j - 6) * WO_BYTES; }
__device__ __forceinline__ int step_src(int hg, int j) { return j == 0 ? hg : j <= hg ? j - 1 : j; }
__device__ __forceinline__ bool tail_first(int hg) { return (hg & 3) == 3; }
__device__ __forceinline__ uint32_t off_ch(int c) { return (c < 3 ? OFF_CH0 : OFF_CH3 - 3 * CH_BYTES) + c * CH_BYTES; }

#define U_PITCH 264
__device__ __align__(1024) uint4 g_U[DIM * U_PITCH];
__device__ __align__(128) uint4 g_O[NCTA * 1280];
__device__ uint4 g_WO[64 * 800];
__device__ uint4 g_halo[NCTA * 2 * 7 * 32];
__device__ __align__(128) float g_gate[SEQ];
__device__ unsigned g_cnt[32 * (1 + 2 * 16 + 8 + NCTA)];
constexpr int C_LAUNCH = 0, C_PREP = 32, C_Y = 32 * 17, C_W = 32 * 33, C_O = 32 * 41;

#define TSM(cond, slot) do { } while (0)
#define TSIF(cond, slot) do { if (__LINE__ >= FENCE_LO && __LINE__ < FENCE_HI) sched_fence(); } while (0)
__device__ __forceinline__ void sched_fence() {
  asm volatile("{\n.reg .pred p;\n.reg .u32 c;\nmov.u32 c, %%clock;\nsetp.eq.u32 p, c, 0;\n@p st.shared.u32 [%0], c;\n}"
               ::"r"(1024 + OFF_EPOCH + 4) : "memory");
}
#define TS(slot) TSIF(true, slot)

struct Params {
  const __nv_bfloat16 *q, *k, *v, *shift_k, *ssm_k, *ssm_D, *wqkv, *wo, *gate_w;
  __nv_bfloat16* out;
  uint32_t zero;
};

constexpr int SPIN_LIMIT = 1 << 17;

__device__ __forceinline__ void mbar_init(uint32_t bar, uint32_t count) {
  asm volatile("mbarrier.init.shared::cta.b64 [%0], %1;" ::"r"(bar), "r"(count) : "memory");
}
__device__ __forceinline__ void mbar_expect_tx(uint32_t bar, uint32_t bytes) {
  asm volatile("mbarrier.arrive.expect_tx.shared::cta.b64 _, [%0], %1;" ::"r"(bar), "r"(bytes) : "memory");
}
__device__ __forceinline__ void mbar_arrive(uint32_t bar) {
  asm volatile("mbarrier.arrive.shared::cta.b64 _, [%0];" ::"r"(bar) : "memory");
}
__device__ __forceinline__ void mbar_wait(uint32_t bar, uint32_t parity) {
  uint32_t ok;
  int spins = 0;
  do {
      asm volatile("{\n.reg .pred p;\nmbarrier.try_wait.parity.shared::cta.b64 p, [%1], %2;\nselp.b32 %0, 1, 0, p;\n}"
                   : "=r"(ok) : "r"(bar), "r"(parity) : "memory");
    if (++spins > SPIN_LIMIT) break;
  } while (!ok);
}
__device__ __forceinline__ unsigned flag_read(const unsigned* p) {
  unsigned v;
  asm volatile("ld.relaxed.gpu.global.u32 %0, [%1];" : "=r"(v) : "l"(p) : "memory");
  return v;
}
__device__ __forceinline__ void flag_poll(const unsigned* p, unsigned target) {
  unsigned v;
  int spins = 0;
  do {
    asm volatile("ld.relaxed.gpu.global.u32 %0, [%1];" : "=r"(v) : "l"(p) : "memory");
    if (++spins > SPIN_LIMIT) break;
  } while ((int)(v - target) < 0);
}
__device__ __forceinline__ void flag_wait(const unsigned* p, unsigned target) {
  flag_poll(p, target);
}
__device__ __forceinline__ void flag_signal(unsigned* p, int n, int lane) {
  if (lane == 0) asm volatile("fence.release.gpu;" ::: "memory");
  __syncwarp();
  if (lane < n) asm volatile("red.relaxed.gpu.global.add.u32 [%0], 1;" ::"l"(p + 32 * lane) : "memory");
}
__device__ __forceinline__ void flag_bump(unsigned* p) {
  asm volatile("red.relaxed.gpu.global.add.u32 [%0], 1;" ::"l"(p) : "memory");
}
__device__ __forceinline__ void fence_async_smem() { asm volatile("fence.proxy.async.shared::cta;" ::: "memory"); }
__device__ __forceinline__ void wg_sync(int id) { asm volatile("bar.sync %0, 128;" ::"r"(id) : "memory"); }

__device__ __forceinline__ void tma_2d(uint32_t dst, const CUtensorMap* tm, int c0, int c1, uint32_t bar) {
  asm volatile("cp.async.bulk.tensor.2d.shared::cluster.global.mbarrier::complete_tx::bytes [%0], [%1, {%3, %4}], [%2];"
               ::"r"(dst), "l"(tm), "r"(bar), "r"(c0), "r"(c1) : "memory");
}
__device__ __forceinline__ void tma_3d(uint32_t dst, const CUtensorMap* tm, int c0, int c1, int c2, uint32_t bar) {
  asm volatile("cp.async.bulk.tensor.3d.shared::cluster.global.mbarrier::complete_tx::bytes [%0], [%1, {%3, %4, %5}], [%2];"
               ::"r"(dst), "l"(tm), "r"(bar), "r"(c0), "r"(c1), "r"(c2) : "memory");
}
__device__ __forceinline__ void bulk_load(uint32_t dst, const void* src, uint32_t bytes, uint32_t bar) {
  asm volatile("cp.async.bulk.shared::cluster.global.mbarrier::complete_tx::bytes [%0], [%1], %2, [%3];"
               ::"r"(dst), "l"(src), "r"(bytes), "r"(bar) : "memory");
}
__device__ __forceinline__ void bulk_store(void* dst, uint32_t src, uint32_t bytes) {
  asm volatile("cp.async.bulk.global.shared::cta.bulk_group [%0], [%1], %2;" ::"l"(dst), "r"(src), "r"(bytes) : "memory");
}
__device__ __forceinline__ void bulk_wait_read() {
  asm volatile("cp.async.bulk.commit_group;\ncp.async.bulk.wait_group.read 0;" ::: "memory");
}

__device__ __forceinline__ void publish(void* dst, uint32_t src, uint32_t bytes) {
  bulk_store(dst, src, bytes);
  bulk_wait_read();
}

__device__ __forceinline__ void wg_fence() { asm volatile("wgmma.fence.sync.aligned;" ::: "memory"); }
__device__ __forceinline__ void wg_commit() { asm volatile("wgmma.commit_group.sync.aligned;" ::: "memory"); }
template <int N> __device__ __forceinline__ void wg_wait() { asm volatile("wgmma.wait_group.sync.aligned %0;" ::"n"(N) : "memory"); }
__device__ __forceinline__ uint32_t desc_lo(uint32_t addr, uint32_t lbo) { return ((addr & 0x3FFFF) >> 4) | ((lbo >> 4) << 16); }
constexpr uint32_t desc_hi(uint32_t sbo, uint32_t swz) { return (sbo >> 4) | (swz << 30); }
constexpr uint32_t HI_SW128 = desc_hi(1024, 1), HI_SW64 = desc_hi(512, 2), HI_SW32 = desc_hi(256, 3), HI_NONE = desc_hi(128, 0);
template <int N> __device__ __forceinline__ void pin(float* d) {
#pragma unroll
  for (int i = 0; i < N; i++) asm volatile("" : "+f"(d[i])::"memory");
}

__device__ __forceinline__ uint32_t lds32(uint32_t a) {
  uint32_t v;
  asm volatile("ld.volatile.shared.u32 %0, [%1];" : "=r"(v) : "r"(a) : "memory");
  return v;
}
__device__ __forceinline__ uint2 ldg64(const void* a) {
  uint2 v;
  asm volatile("ld.global.nc.v2.u32 {%0, %1}, [%2];" : "=r"(v.x), "=r"(v.y) : "l"(a) : "memory");
  return v;
}
__device__ __forceinline__ void ldsm4(uint32_t* r, uint32_t a) {
  asm volatile("ldmatrix.sync.aligned.m8n8.x4.shared.b16 {%0, %1, %2, %3}, [%4];"
               : "=r"(r[0]), "=r"(r[1]), "=r"(r[2]), "=r"(r[3]) : "r"(a) : "memory");
}
__device__ __forceinline__ void ldsm4t(uint32_t* r, uint32_t a) {
  asm volatile("ldmatrix.sync.aligned.m8n8.x4.trans.shared.b16 {%0, %1, %2, %3}, [%4];"
               : "=r"(r[0]), "=r"(r[1]), "=r"(r[2]), "=r"(r[3]) : "r"(a) : "memory");
}
__device__ __forceinline__ uint2 lds64(uint32_t a) {
  uint2 v;
  asm volatile("ld.shared.v2.u32 {%0, %1}, [%2];" : "=r"(v.x), "=r"(v.y) : "r"(a) : "memory");
  return v;
}
__device__ __forceinline__ uint4 lds128(uint32_t a) {
  uint4 v;
  asm volatile("ld.shared.v4.u32 {%0, %1, %2, %3}, [%4];" : "=r"(v.x), "=r"(v.y), "=r"(v.z), "=r"(v.w) : "r"(a) : "memory");
  return v;
}
__device__ __forceinline__ void sts128(uint32_t a, uint32_t x, uint32_t y, uint32_t z, uint32_t w) {
  asm volatile("st.shared.v4.u32 [%0], {%1, %2, %3, %4};" ::"r"(a), "r"(x), "r"(y), "r"(z), "r"(w) : "memory");
}
__device__ __forceinline__ void stsm4(uint32_t a, const uint32_t* r) {
  asm volatile("stmatrix.sync.aligned.m8n8.x4.shared.b16 [%0], {%1, %2, %3, %4};" ::"r"(a), "r"(r[0]), "r"(r[1]), "r"(r[2]), "r"(r[3]) : "memory");
}
__device__ __forceinline__ uint32_t pack2(float lo, float hi) {
  uint32_t r;
  asm("cvt.rn.bf16x2.f32 %0, %1, %2;" : "=r"(r) : "f"(hi), "f"(lo));
  return r;
}
__device__ __forceinline__ uint32_t movm(uint32_t a) {
  uint32_t d;
  asm volatile("movmatrix.sync.aligned.m8n8.trans.b16 %0, %1;" : "=r"(d) : "r"(a));
  return d;
}
__device__ __forceinline__ uint32_t bmul(uint32_t a, uint32_t b) {
  uint32_t d;
  asm("mul.rn.bf16x2 %0, %1, %2;" : "=r"(d) : "r"(a), "r"(b));
  return d;
}
__device__ __forceinline__ uint32_t badd(uint32_t a, uint32_t b) {
  uint32_t d;
  asm("add.rn.bf16x2 %0, %1, %2;" : "=r"(d) : "r"(a), "r"(b));
  return d;
}
__device__ __forceinline__ uint32_t bfma(uint32_t a, uint32_t b, uint32_t c) {
  uint32_t d;
  asm("fma.rn.bf16x2 %0, %1, %2, %3;" : "=r"(d) : "r"(a), "r"(b), "r"(c));
  return d;
}
__device__ __forceinline__ float bf_lo(uint32_t x) { return __uint_as_float(x << 16); }
__device__ __forceinline__ float bf_hi(uint32_t x) { return __uint_as_float(x & 0xFFFF0000u); }
__device__ __forceinline__ float ex2(float x) {
  float y;
  asm("ex2.approx.ftz.f32 %0, %1;" : "=f"(y) : "f"(x));
  return y;
}
__device__ __forceinline__ float rcp(float x) {
  float y;
  asm("rcp.approx.ftz.f32 %0, %1;" : "=f"(y) : "f"(x));
  return y;
}
__device__ __forceinline__ void mma16816(float* d, uint32_t a0, uint32_t a1, uint32_t a2, uint32_t a3, uint32_t b0, uint32_t b1) {
  asm volatile("mma.sync.aligned.m16n8k16.row.col.f32.bf16.bf16.f32 {%0, %1, %2, %3}, {%4, %5, %6, %7}, {%8, %9}, {%0, %1, %2, %3};"
               : "+f"(d[0]), "+f"(d[1]), "+f"(d[2]), "+f"(d[3])
               : "r"(a0), "r"(a1), "r"(a2), "r"(a3), "r"(b0), "r"(b1));
}
__device__ __forceinline__ void mma1688(float* d, uint32_t a0, uint32_t a1, uint32_t b0) {
  asm volatile("mma.sync.aligned.m16n8k8.row.col.f32.bf16.bf16.f32 {%0, %1, %2, %3}, {%4, %5}, {%6}, {%0, %1, %2, %3};"
               : "+f"(d[0]), "+f"(d[1]), "+f"(d[2]), "+f"(d[3])
               : "r"(a0), "r"(a1), "r"(b0));
}

template <int N> struct WgRS;
template <int N> struct WgSST;
template <> struct WgRS<32> {
  template <uint32_t HB>
  static __device__ __forceinline__ void mma(float* d, const uint32_t* a, uint32_t db) {
    asm volatile("{\n.reg .pred p;\n.reg .b64 db;\nsetp.ne.b32 p, %22, 0;\n"
      "mov.b64 db, {%20, %21};\n"
      "wgmma.mma_async.sync.aligned.m64n32k16.f32.bf16.bf16 {"
      "%0, %1, %2, %3, %4, %5, %6, %7, %8, %9, %10, %11, %12, %13, %14, %15"
      "}, {%16, %17, %18, %19}, db, p, 1, 1, 1;\n}\n"
      : "+f"(d[0]), "+f"(d[1]), "+f"(d[2]), "+f"(d[3]), "+f"(d[4]), "+f"(d[5]), "+f"(d[6]), "+f"(d[7]),
        "+f"(d[8]), "+f"(d[9]), "+f"(d[10]), "+f"(d[11]), "+f"(d[12]), "+f"(d[13]), "+f"(d[14]), "+f"(d[15])
      : "r"(a[0]), "r"(a[1]), "r"(a[2]), "r"(a[3]), "r"(db), "n"(HB), "n"(1));
  }
  template <uint32_t HB>
  static __device__ __forceinline__ void set(float* d, const uint32_t* a, uint32_t db) {
    asm volatile("{\n.reg .pred p;\n.reg .b64 db;\nsetp.ne.b32 p, %22, 0;\n"
      "mov.b64 db, {%20, %21};\n"
      "wgmma.mma_async.sync.aligned.m64n32k16.f32.bf16.bf16 {"
      "%0, %1, %2, %3, %4, %5, %6, %7, %8, %9, %10, %11, %12, %13, %14, %15"
      "}, {%16, %17, %18, %19}, db, p, 1, 1, 1;\n}\n"
      : "=f"(d[0]), "=f"(d[1]), "=f"(d[2]), "=f"(d[3]), "=f"(d[4]), "=f"(d[5]), "=f"(d[6]), "=f"(d[7]),
        "=f"(d[8]), "=f"(d[9]), "=f"(d[10]), "=f"(d[11]), "=f"(d[12]), "=f"(d[13]), "=f"(d[14]), "=f"(d[15])
      : "r"(a[0]), "r"(a[1]), "r"(a[2]), "r"(a[3]), "r"(db), "n"(HB), "n"(0));
  }
};
template <> struct WgRS<64> {
  template <uint32_t HB>
  static __device__ __forceinline__ void mma(float* d, const uint32_t* a, uint32_t db) {
    asm volatile("{\n.reg .pred p;\n.reg .b64 db;\nsetp.ne.b32 p, %38, 0;\n"
      "mov.b64 db, {%36, %37};\n"
      "wgmma.mma_async.sync.aligned.m64n64k16.f32.bf16.bf16 {"
      "%0, %1, %2, %3, %4, %5, %6, %7, %8, %9, %10, %11, %12, %13, %14, %15, "
      "%16, %17, %18, %19, %20, %21, %22, %23, %24, %25, %26, %27, %28, %29, %30, %31"
      "}, {%32, %33, %34, %35}, db, p, 1, 1, 1;\n}\n"
      : "+f"(d[0]), "+f"(d[1]), "+f"(d[2]), "+f"(d[3]), "+f"(d[4]), "+f"(d[5]), "+f"(d[6]), "+f"(d[7]),
        "+f"(d[8]), "+f"(d[9]), "+f"(d[10]), "+f"(d[11]), "+f"(d[12]), "+f"(d[13]), "+f"(d[14]), "+f"(d[15]),
        "+f"(d[16]), "+f"(d[17]), "+f"(d[18]), "+f"(d[19]), "+f"(d[20]), "+f"(d[21]), "+f"(d[22]), "+f"(d[23]),
        "+f"(d[24]), "+f"(d[25]), "+f"(d[26]), "+f"(d[27]), "+f"(d[28]), "+f"(d[29]), "+f"(d[30]), "+f"(d[31])
      : "r"(a[0]), "r"(a[1]), "r"(a[2]), "r"(a[3]), "r"(db), "n"(HB), "n"(1));
  }
  template <uint32_t HB>
  static __device__ __forceinline__ void set(float* d, const uint32_t* a, uint32_t db) {
    asm volatile("{\n.reg .pred p;\n.reg .b64 db;\nsetp.ne.b32 p, %38, 0;\n"
      "mov.b64 db, {%36, %37};\n"
      "wgmma.mma_async.sync.aligned.m64n64k16.f32.bf16.bf16 {"
      "%0, %1, %2, %3, %4, %5, %6, %7, %8, %9, %10, %11, %12, %13, %14, %15, "
      "%16, %17, %18, %19, %20, %21, %22, %23, %24, %25, %26, %27, %28, %29, %30, %31"
      "}, {%32, %33, %34, %35}, db, p, 1, 1, 1;\n}\n"
      : "=f"(d[0]), "=f"(d[1]), "=f"(d[2]), "=f"(d[3]), "=f"(d[4]), "=f"(d[5]), "=f"(d[6]), "=f"(d[7]),
        "=f"(d[8]), "=f"(d[9]), "=f"(d[10]), "=f"(d[11]), "=f"(d[12]), "=f"(d[13]), "=f"(d[14]), "=f"(d[15]),
        "=f"(d[16]), "=f"(d[17]), "=f"(d[18]), "=f"(d[19]), "=f"(d[20]), "=f"(d[21]), "=f"(d[22]), "=f"(d[23]),
        "=f"(d[24]), "=f"(d[25]), "=f"(d[26]), "=f"(d[27]), "=f"(d[28]), "=f"(d[29]), "=f"(d[30]), "=f"(d[31])
      : "r"(a[0]), "r"(a[1]), "r"(a[2]), "r"(a[3]), "r"(db), "n"(HB), "n"(0));
  }
};
template <> struct WgSST<48> {
  template <uint32_t HA, uint32_t HB>
  static __device__ __forceinline__ void mma(float* d, uint32_t da, uint32_t db, int sc) {
    asm volatile("{\n.reg .pred p;\n.reg .b64 da, db;\nsetp.ne.b32 p, %28, 0;\n"
      "mov.b64 da, {%24, %25};\nmov.b64 db, {%26, %27};\n"
      "wgmma.mma_async.sync.aligned.m64n48k16.f32.bf16.bf16 {"
      "%0, %1, %2, %3, %4, %5, %6, %7, %8, %9, %10, %11, %12, %13, %14, %15, "
      "%16, %17, %18, %19, %20, %21, %22, %23"
      "}, da, db, p, 1, 1, 0, 1;\n}\n"
      : "+f"(d[0]), "+f"(d[1]), "+f"(d[2]), "+f"(d[3]), "+f"(d[4]), "+f"(d[5]), "+f"(d[6]), "+f"(d[7]),
        "+f"(d[8]), "+f"(d[9]), "+f"(d[10]), "+f"(d[11]), "+f"(d[12]), "+f"(d[13]), "+f"(d[14]), "+f"(d[15]),
        "+f"(d[16]), "+f"(d[17]), "+f"(d[18]), "+f"(d[19]), "+f"(d[20]), "+f"(d[21]), "+f"(d[22]), "+f"(d[23])
      : "r"(da), "n"(HA), "r"(db), "n"(HB), "r"(sc));
  }
};
template <> struct WgSST<80> {
  template <uint32_t HA, uint32_t HB>
  static __device__ __forceinline__ void mma(float* d, uint32_t da, uint32_t db, int sc) {
    asm volatile("{\n.reg .pred p;\n.reg .b64 da, db;\nsetp.ne.b32 p, %44, 0;\n"
      "mov.b64 da, {%40, %41};\nmov.b64 db, {%42, %43};\n"
      "wgmma.mma_async.sync.aligned.m64n80k16.f32.bf16.bf16 {"
      "%0, %1, %2, %3, %4, %5, %6, %7, %8, %9, %10, %11, %12, %13, %14, %15, "
      "%16, %17, %18, %19, %20, %21, %22, %23, %24, %25, %26, %27, %28, %29, %30, %31, "
      "%32, %33, %34, %35, %36, %37, %38, %39"
      "}, da, db, p, 1, 1, 0, 1;\n}\n"
      : "+f"(d[0]), "+f"(d[1]), "+f"(d[2]), "+f"(d[3]), "+f"(d[4]), "+f"(d[5]), "+f"(d[6]), "+f"(d[7]),
        "+f"(d[8]), "+f"(d[9]), "+f"(d[10]), "+f"(d[11]), "+f"(d[12]), "+f"(d[13]), "+f"(d[14]), "+f"(d[15]),
        "+f"(d[16]), "+f"(d[17]), "+f"(d[18]), "+f"(d[19]), "+f"(d[20]), "+f"(d[21]), "+f"(d[22]), "+f"(d[23]),
        "+f"(d[24]), "+f"(d[25]), "+f"(d[26]), "+f"(d[27]), "+f"(d[28]), "+f"(d[29]), "+f"(d[30]), "+f"(d[31]),
        "+f"(d[32]), "+f"(d[33]), "+f"(d[34]), "+f"(d[35]), "+f"(d[36]), "+f"(d[37]), "+f"(d[38]), "+f"(d[39])
      : "r"(da), "n"(HA), "r"(db), "n"(HB), "r"(sc));
  }
};
template <> struct WgSST<192> {
  template <uint32_t HA, uint32_t HB>
  static __device__ __forceinline__ void mma(float* d, uint32_t da, uint32_t db, int sc) {
    asm volatile("{\n.reg .pred p;\n.reg .b64 da, db;\nsetp.ne.b32 p, %100, 0;\n"
      "mov.b64 da, {%96, %97};\nmov.b64 db, {%98, %99};\n"
      "wgmma.mma_async.sync.aligned.m64n192k16.f32.bf16.bf16 {"
      "%0, %1, %2, %3, %4, %5, %6, %7, %8, %9, %10, %11, %12, %13, %14, %15, "
      "%16, %17, %18, %19, %20, %21, %22, %23, %24, %25, %26, %27, %28, %29, %30, %31, "
      "%32, %33, %34, %35, %36, %37, %38, %39, %40, %41, %42, %43, %44, %45, %46, %47, "
      "%48, %49, %50, %51, %52, %53, %54, %55, %56, %57, %58, %59, %60, %61, %62, %63, "
      "%64, %65, %66, %67, %68, %69, %70, %71, %72, %73, %74, %75, %76, %77, %78, %79, "
      "%80, %81, %82, %83, %84, %85, %86, %87, %88, %89, %90, %91, %92, %93, %94, %95"
      "}, da, db, p, 1, 1, 0, 1;\n}\n"
      : "+f"(d[0]), "+f"(d[1]), "+f"(d[2]), "+f"(d[3]), "+f"(d[4]), "+f"(d[5]), "+f"(d[6]), "+f"(d[7]),
        "+f"(d[8]), "+f"(d[9]), "+f"(d[10]), "+f"(d[11]), "+f"(d[12]), "+f"(d[13]), "+f"(d[14]), "+f"(d[15]),
        "+f"(d[16]), "+f"(d[17]), "+f"(d[18]), "+f"(d[19]), "+f"(d[20]), "+f"(d[21]), "+f"(d[22]), "+f"(d[23]),
        "+f"(d[24]), "+f"(d[25]), "+f"(d[26]), "+f"(d[27]), "+f"(d[28]), "+f"(d[29]), "+f"(d[30]), "+f"(d[31]),
        "+f"(d[32]), "+f"(d[33]), "+f"(d[34]), "+f"(d[35]), "+f"(d[36]), "+f"(d[37]), "+f"(d[38]), "+f"(d[39]),
        "+f"(d[40]), "+f"(d[41]), "+f"(d[42]), "+f"(d[43]), "+f"(d[44]), "+f"(d[45]), "+f"(d[46]), "+f"(d[47]),
        "+f"(d[48]), "+f"(d[49]), "+f"(d[50]), "+f"(d[51]), "+f"(d[52]), "+f"(d[53]), "+f"(d[54]), "+f"(d[55]),
        "+f"(d[56]), "+f"(d[57]), "+f"(d[58]), "+f"(d[59]), "+f"(d[60]), "+f"(d[61]), "+f"(d[62]), "+f"(d[63]),
        "+f"(d[64]), "+f"(d[65]), "+f"(d[66]), "+f"(d[67]), "+f"(d[68]), "+f"(d[69]), "+f"(d[70]), "+f"(d[71]),
        "+f"(d[72]), "+f"(d[73]), "+f"(d[74]), "+f"(d[75]), "+f"(d[76]), "+f"(d[77]), "+f"(d[78]), "+f"(d[79]),
        "+f"(d[80]), "+f"(d[81]), "+f"(d[82]), "+f"(d[83]), "+f"(d[84]), "+f"(d[85]), "+f"(d[86]), "+f"(d[87]),
        "+f"(d[88]), "+f"(d[89]), "+f"(d[90]), "+f"(d[91]), "+f"(d[92]), "+f"(d[93]), "+f"(d[94]), "+f"(d[95])
      : "r"(da), "n"(HA), "r"(db), "n"(HB), "r"(sc));
  }
};

struct FftConst {
  uint32_t f[2][4], fi[4][4];
  uint32_t ta[2][2], tb[2][2];
};
__device__ __forceinline__ void cis(int m, float scale, float& c, float& s) {
  const float a = (float)m * (-6.283185307179586f * scale);
  c = __cosf(a);
  s = __sinf(a);
}
__device__ __forceinline__ void fft_tables(uint32_t (&v)[12], int tw) {
  const int row = tw >> 2, ch = tw & 3;
#pragma unroll
  for (int i = 0; i < 4; i++) {
    float c[2], s[2], x[2];
#pragma unroll
    for (int e = 0; e < 2; e++) {
      cis((((32 * (8 * ch + 2 * i + e) + 15) * (4 * row - 63) + 2048) & 4095) - 2048, 1.f / 4096, c[e], s[e]);
      float gc, gs;
      cis((((row & 15) * (8 * (ch & 1) + 2 * i + e) + 8) & 15) - 8, 1.f / 16, gc, gs);
      x[e] = (row >> 4) == (ch >> 1) ? gc : (ch >> 1) ? gs : -gs;
    }
    v[i] = pack2(c[0] * 0.125f, c[1] * 0.125f);
    v[4 + i] = pack2(s[0] * 0.125f, s[1] * 0.125f);
    v[8 + i] = pack2(x[0], x[1]);
  }
#pragma unroll
  for (int i = 0; i < 12; i++) asm volatile("" : "+r"(v[i]));
}
__device__ __forceinline__ void fft_tables_store(const uint32_t (&v)[12], uint32_t sb, int tw) {
  const int row = tw >> 2;
  const uint32_t x = ((tw ^ (row >> 1)) & 3) << 4, a = sb + OFF_FT + (16 * (row >> 3) + (row & 7)) * 64 + x;
  sts128(a, v[0], v[1], v[2], v[3]);
  sts128(a + 512, v[4], v[5], v[6], v[7]);
  sts128(sb + OFF_GT + row * 64 + x, v[8], v[9], v[10], v[11]);
}
__device__ __forceinline__ void fft_twiddles(uint32_t (&v)[2], int tw) {
  float a[2], s[2];
#pragma unroll
  for (int i = 0; i < 2; i++) {
    float c;
    cis((2 * (2 * (tw & 3) + i) - 15) * (4 * (tw >> 2) - 63), 1.f / 4096, c, s[i]);
    a[i] = __fdividef(-s[i], 1.f + c);
  }
  v[0] = pack2(a[0], a[1]);
  v[1] = pack2(s[0], s[1]);
  asm volatile("" : "+r"(v[0]), "+r"(v[1]));
}
__device__ __forceinline__ void fft_matrices(FftConst& k, uint32_t sb, int w, int lane) {
  const uint32_t x = (lane >> 1) & 3;
  const uint2 t0 = lds64(sb + OFF_TT + 256 * w + 8 * lane), t1 = lds64(sb + OFF_TT + 256 * w + 8 * (lane ^ 3));
  k.ta[0][0] = t0.x;
  k.tb[0][0] = t0.y;
  k.ta[1][1] = __byte_perm(t1.x, 0, 0x1032);
  k.tb[1][1] = __byte_perm(t1.y, 0, 0x1032);
#pragma unroll
  for (int j = 0; j < 2; j++) {
    k.ta[1 - j][j] = k.ta[j][j] ^ 0x80008000u;
    k.tb[1 - j][j] = k.tb[j][j] ^ 0x80008000u;
    asm volatile("" : "+r"(k.ta[0][j]), "+r"(k.tb[0][j]), "+r"(k.ta[1][j]), "+r"(k.tb[1][j]));
  }
#pragma unroll
  for (int i = 0; i < 2; i++) {
    ldsm4(k.f[i], sb + OFF_FT + (16 * w + (lane & 15)) * 64 + (((2 * i + (lane >> 4)) ^ x) << 4));
    ldsm4t(k.fi[i], sb + OFF_FT + (32 * i + lane) * 64 + ((w ^ x) << 4));
#pragma unroll
    for (int j = 0; j < 4; j++) {
      k.fi[2 + i][j] = (j & 1) ? k.fi[i][j - 1] ^ 0x80008000u : k.fi[i][j + 1];
      asm volatile("" : "+r"(k.fi[2 + i][j]));
    }
  }
}
__device__ __forceinline__ void rot(uint32_t& x, uint32_t& y, uint32_t a, uint32_t b) {
  x = bfma(a, y, x);
  y = bfma(b, x, y);
  x = bfma(a, y, x);
}
__device__ __forceinline__ void twiddle_fwd(uint32_t (&a)[4][4], float* d, const FftConst& k) {
#pragma unroll
  for (int q = 0; q < 4; q++)
#pragma unroll
    for (int j = 0; j < 2; j++) {
      const float* x = d + 8 * q + 4 * j;
      uint32_t re = pack2(x[0], x[1]), im = pack2(x[2], x[3]);
      rot(re, im, k.ta[0][j], k.tb[0][j]);
      a[q & 2][2 * j + (q & 1)] = re;
      a[(q & 2) + 1][2 * j + (q & 1)] = im;
    }
}
__device__ __forceinline__ void g_step(float* d, const uint32_t (&a)[4][4], uint32_t dre, uint32_t dim) {
  WgRS<32>::set<HI_SW64>(d, a[0], dre);
  WgRS<32>::set<HI_SW64>(d + 16, a[2], dre);
  WgRS<32>::mma<HI_SW64>(d, a[1], dim);
  WgRS<32>::mma<HI_SW64>(d + 16, a[3], dim);
  wg_commit();
}

__device__ __forceinline__ void products(uint32_t (&a)[4][4], const float* H, const float* U, int p) {
#pragma unroll
  for (int j = 0; j < 2; j++)
#pragma unroll
    for (int m = 2 * p; m < 2 * p + 2; m++) {
      float pr[2], pi[2];
#pragma unroll
      for (int x = 0; x < 2; x++)
#pragma unroll
        for (int q = 0; q <= m; q++) {
          const int ih = 16 * (q >> 1) + 2 * (q & 1) + 4 * j + x, iu = 16 * ((m - q) >> 1) + 2 * ((m - q) & 1) + 4 * j + x;
          pr[x] = q ? fmaf(H[ih], U[iu], pr[x]) : H[ih] * U[iu];
          pi[x] = q ? fmaf(H[ih], U[iu + 8], pi[x]) : H[ih] * U[iu + 8];
          pr[x] = fmaf(-H[ih + 8], U[iu + 8], pr[x]);
          pi[x] = fmaf(H[ih + 8], U[iu], pi[x]);
        }
      a[m & 2][2 * j + (m & 1)] = pack2(pr[0], pr[1]);
      a[(m & 2) + 1][2 * j + (m & 1)] = pack2(pi[0], pi[1]);
    }
}

__device__ __forceinline__ void conv_channel(const FftConst& k, uint32_t sb, int c, int wg, int w, int lane) {
  const uint32_t cb = sb + off_ch(c), bars = sb + OFF_BAR;
  const uint32_t du = desc_lo(cb, 1024), dg = desc_lo(sb + OFF_GT, 16), dz = desc_lo(cb + U_BYTES, 16);
  float U[32], H[32];
  uint32_t a[4][4], e[4][4];
  const float dv = __uint_as_float(lds32(sb + OFF_D + 4 * c));
  wg_fence();
  WgRS<64>::set<HI_SW32>(H, k.f[0], du + 256);
  WgRS<64>::mma<HI_SW32>(H, k.f[1], du + 256 + 32);
  wg_commit();
  wg_wait<0>();
  pin<32>(H);
  twiddle_fwd(a, H, k);
  mbar_wait(bars + 8 * (B_U + (c < 3 ? c : 3)), 0);
  TSM(w == 0 && c < 3, 7 + wg);
  wg_fence();
  WgRS<64>::set<HI_SW32>(U, k.f[0], du);
  WgRS<64>::mma<HI_SW32>(U, k.f[1], du + 32);
  wg_commit();
  g_step(H, a, dg, dg + 64);
  wg_wait<1>();
  pin<32>(U);
  twiddle_fwd(e, U, k);
  wg_fence();
  g_step(U, e, dg, dg + 64);
  wg_wait<0>();
  pin<32>(U);
  pin<32>(H);
#pragma unroll
  for (int j = 0; j < 4; j++) H[4 * (j >> 1) + (j & 1)] += dv;
  float V[32];
#pragma unroll
  for (int p = 0; p < 2; p++) {
    products(a, H, U, p);
    wg_fence();
    WgRS<32>::set<HI_SW64>(V + 16 * p, a[2 * p], dg + 64);
    WgRS<32>::mma<HI_SW64>(V + 16 * p, a[2 * p + 1], dg);
    wg_commit();
  }
  const uint32_t za = cb + U_BYTES + (8 * w + (lane & 7)) * 128 + (((lane >> 3) ^ (lane & 7)) << 4);
  const uint32_t ya = cb + (lane >> 4) * 1024 + (8 * w + (lane & 7)) * 32 + ((((lane >> 3) ^ (lane >> 2)) & 1) << 4);
  wg_sync(1 + wg);
#pragma unroll
  for (int p = 0; p < 2; p++) {
    if (p == 0) wg_wait<1>();
    else wg_wait<0>();
    pin<16>(V + 16 * p);
#pragma unroll
    for (int i = 0; i < 4; i++) {
      const int j = i & 1;
      const float* x = V + 16 * p + 4 * j + (i & 2);
      e[p][i] = pack2(x[8], x[9]);
      e[2 + p][i] = pack2(x[0], x[1]);
      rot(e[p][i], e[2 + p][i], k.ta[1][j], k.tb[1][j]);
    }
    stsm4(za ^ (64 * p), e[p]);
    stsm4((za ^ (64 * p)) + 4096, e[2 + p]);
  }
  fence_async_smem();
  wg_sync(1 + wg);
  wg_fence();
  WgRS<64>::set<HI_SW128>(H, k.fi[0], dz);
#pragma unroll
  for (int ks = 1; ks < 4; ks++) WgRS<64>::mma<HI_SW128>(H, k.fi[ks], dz + 128 * ks);
  wg_commit();
  wg_wait<0>();
  pin<32>(H);
  if (lane == 0) mbar_arrive(bars + 8 * B_CVD);
  TSIF(w == 0, 88 + c);
#pragma unroll
  for (int j = 0; j < 8; j++)
    a[j >> 2][j & 3] = j < 2 ? pack2(H[4 * j], H[4 * j + 1]) : pack2(H[4 * j] + H[4 * j - 6], H[4 * j + 1] + H[4 * j - 5]);
  stsm4(ya, a[0]);
  stsm4(ya + 2048, a[1]);
  fence_async_smem();
  __syncwarp();
}

__device__ __forceinline__ void prep_slab(uint4* res, const uint2* sw, uint32_t sb, int slab, int w, int lane) {
  const int t = lane & 3, tp = (lane & 7) >> 1, pos = 8 * tp + 2 * (((lane >> 3) + tp) & 3) + (lane & 1);
  const uint32_t base = sb + OFF_KVS + slab * KVS_BYTES + pos * 128;
  uint32_t kk[2][4][4], vv[2][4];
  mbar_wait(sb + OFF_BAR + 8 * (B_KV + slab), 0);
#pragma unroll
  for (int h = 0; h < 2; h++) {
#pragma unroll
    for (int j = 0; j < 4; j++) {
      const uint32_t a = base + 128 * j;
      ldsm4t(kk[h][j], a + (((w + 4 * h) ^ ((a >> 7) & 7)) << 4));
    }
    const uint32_t a = base + KVS_V;
    ldsm4t(vv[h], a + (((w + 4 * h) ^ ((a >> 7) & 7)) << 4));
  }
#pragma unroll
  for (int h = 0; h < 2; h++) {
    uint32_t (&k)[4][4] = kk[h];
    uint32_t (&v)[4] = vv[h];
    const uint32_t w0 = __byte_perm(sw[h].x, 0, 0x1010), w1 = __byte_perm(sw[h].x, 0, 0x3232);
    const uint32_t w2 = __byte_perm(sw[h].y, 0, 0x1010), w3 = __byte_perm(sw[h].y, 0, 0x3232);
#pragma unroll
    for (int m = 0; m < 4; m++)
      v[m] = bmul(badd(badd(badd(bmul(k[0][m], w3), bmul(k[1][m], w2)), bmul(k[2][m], w1)), bmul(k[3][m], w0)), v[m]);
    uint32_t a[4];
#pragma unroll
    for (int m = 0; m < 4; m++) a[m] = (t & 1) ? v[(m + 3) & 3] : v[m];
    res[h] = (t & 2) ? make_uint4(a[2], a[3], a[0], a[1]) : make_uint4(a[0], a[1], a[2], a[3]);
  }
}

__device__ __forceinline__ void prep_gate(const Params& p, uint32_t sb, int b, int w, int lane) {
  uint2 gw[5], x[4][5];
#pragma unroll
  for (int j = 0; j < 5; j++) gw[j] = ldg64(reinterpret_cast<const uint2*>(p.gate_w) + lane + 32 * j);
#pragma unroll
  for (int i = 0; i < 4; i++)
#pragma unroll
    for (int j = 0; j < 5; j++)
      x[i][j] = ldg64(reinterpret_cast<const uint2*>(p.q) + (16 * b + 4 * w + i) * (DIM / 4) + lane + 32 * j);
  float s[4];
#pragma unroll
  for (int i = 0; i < 4; i++) {
    s[i] = 0.f;
#pragma unroll
    for (int j = 0; j < 5; j++) {
      const uint32_t m0 = bmul(x[i][j].x, gw[j].x), m1 = bmul(x[i][j].y, gw[j].y);
      s[i] += (bf_lo(m0) + bf_hi(m0)) + (bf_lo(m1) + bf_hi(m1));
    }
  }
  const bool h = lane & 16, q = lane & 8;
  const float a = (h ? s[2] : s[0]) + __shfl_xor_sync(0xffffffffu, h ? s[0] : s[2], 16);
  const float c = (h ? s[3] : s[1]) + __shfl_xor_sync(0xffffffffu, h ? s[1] : s[3], 16);
  float z = (q ? c : a) + __shfl_xor_sync(0xffffffffu, q ? a : c, 8);
#pragma unroll
  for (int o = 4; o > 0; o >>= 1) z += __shfl_xor_sync(0xffffffffu, z, o);
  z = bf_lo(pack2(z, 0.f));
  z = bf_lo(pack2(__fdividef(1.f, 1.f + __expf(-z)), 0.f));
  mbar_wait(sb + OFF_BAR + 8 * B_S3, 0);
  if ((lane & 7) == 0) asm volatile("st.shared.f32 [%0], %1;" ::"r"(sb + OFF_GATE + 64 * (b & 7) + 16 * w + (lane >> 1)), "f"(z) : "memory");
  fence_async_smem();
}

__device__ __forceinline__ uint32_t bmax(uint32_t a, uint32_t b) {
  uint32_t d;
  asm("max.bf16x2 %0, %1, %2;" : "=r"(d) : "r"(a), "r"(b));
  return d;
}
__device__ __forceinline__ void softmax_two(const float (&l)[2][2], uint32_t& p0, uint32_t& p1) {
  constexpr float kScale = 0.22360679774997896f, kLog2e = 1.4426950408889634f;
  const uint32_t r0 = pack2(l[0][0], l[1][0]), r1 = pack2(l[0][1], l[1][1]);
  const uint32_t x0 = pack2(bf_lo(r0) * kScale, bf_hi(r0) * kScale), x1 = pack2(bf_lo(r1) * kScale, bf_hi(r1) * kScale);
  uint32_t m = bmax(x0, x1);
  m = bmax(m, __shfl_xor_sync(0xffffffffu, m, 1));
  m = bmax(m, __shfl_xor_sync(0xffffffffu, m, 2));
  const float m0 = bf_lo(m) * kLog2e, m1 = bf_hi(m) * kLog2e;
  p0 = pack2(ex2(bf_lo(x0) * kLog2e - m0), ex2(bf_lo(x1) * kLog2e - m0));
  p1 = pack2(ex2(bf_hi(x0) * kLog2e - m1), ex2(bf_hi(x1) * kLog2e - m1));
}

__device__ __forceinline__ void halo_read(uint32_t (&kpv)[10], uint32_t (&vpv)[10], uint32_t (&tg)[7], const uint4* hp) {
#pragma unroll
  for (int j = 0; j < 7; j++) {
    uint32_t x0, x1, x2;
    asm volatile("ld.relaxed.gpu.global.v4.u32 {%0, %1, %2, %3}, [%4];"
                 : "=r"(x0), "=r"(x1), "=r"(x2), "=r"(tg[j]) : "l"(hp + 32 * j) : "memory");
    if (j < 4) kpv[3 * j] = x0; else vpv[3 * j - 10] = x0;
    if (j < 3) kpv[3 * j + 1] = x1; else vpv[3 * j - 9] = x1;
    if (j < 3) kpv[3 * j + 2] = x2; else if (j < 6) vpv[3 * j - 8] = x2;
  }
}

template <int ROT>
__device__ __forceinline__ void pack_qkv(const float* acc, uint32_t (&qlo)[10], uint32_t (&qhi)[10], uint32_t (&klo)[10],
                                         uint32_t (&khi)[10], uint32_t (&vlo)[10], uint32_t (&vhi)[10]) {
#pragma unroll
  for (int j = 0; j < 10; j++) {
    const int x = (j + ROT) % 10, tq = x < 8 ? x : 16 + x, tk = x < 8 ? 8 + x : 18 + x, tv = x < 8 ? 16 + x : 20 + x;
    khi[j] = pack2(acc[4 * tk + 2], acc[4 * tk + 3]);
    vhi[j] = movm(pack2(acc[4 * tv + 2], acc[4 * tv + 3]));
    qlo[j] = pack2(acc[4 * tq], acc[4 * tq + 1]);
    qhi[j] = pack2(acc[4 * tq + 2], acc[4 * tq + 3]);
    klo[j] = pack2(acc[4 * tk], acc[4 * tk + 1]);
    vlo[j] = pack2(acc[4 * tv], acc[4 * tv + 1]);
    asm volatile("" : "+r"(khi[j]), "+r"(qlo[j]), "+r"(qhi[j]), "+r"(klo[j]), "+r"(vlo[j]));
  }
}

template <int ROT> __device__ __forceinline__ void halo_send(const float* acc, uint4* ho, uint32_t tag) {
#pragma unroll
  for (int j = 0; j < 7; j++) {
    uint32_t x[3];
#pragma unroll
    for (int e = 0; e < 3; e++) {
      const int i = 3 * j + e, y = (i % 10 + ROT) % 10, tk = y < 8 ? 8 + y : 18 + y, tv = y < 8 ? 16 + y : 20 + y;
      x[e] = i < 10 ? pack2(acc[4 * tk + 2], acc[4 * tk + 3]) : i < 20 ? movm(pack2(acc[4 * tv + 2], acc[4 * tv + 3])) : 0u;
    }
    asm volatile("st.relaxed.gpu.global.v4.u32 [%0], {%1, %2, %3, %4};" ::"l"(ho + 32 * j), "r"(x[0]), "r"(x[1]), "r"(x[2]), "r"(tag) : "memory");
  }
}

__device__ __forceinline__ void attention(float* acc, uint32_t sb, int b, int par, int w, int lane, uint32_t tag, FftConst& fc) {
  const int g = lane >> 2, t = lane & 3;
  uint32_t klo[10], khi[10], vlo[10], vhi[10], qlo[10], qhi[10], kpv[10], vpv[10];
  if (w == 3 && b < NCTA - 8) {
    uint4* ho = g_halo + (b * 2 + par) * 224 + lane;
    if (tail_first(b & 7)) halo_send<8>(acc, ho, tag);
    else halo_send<0>(acc, ho, tag);
    TSIF(par == 0, 76);
    pin<120>(acc);
  }
  if (tail_first(b & 7)) pack_qkv<8>(acc, qlo, qhi, klo, khi, vlo, vhi);
  else pack_qkv<0>(acc, qlo, qhi, klo, khi, vlo, vhi);
  const uint32_t xa = sb + OFF_KVX + (par * 3) * 2560 + lane * 16;
  if (w < 3) {
    sts128(xa + w * 2560, khi[0], khi[1], khi[2], khi[3]);
    sts128(xa + w * 2560 + 512, khi[4], khi[5], khi[6], khi[7]);
    sts128(xa + w * 2560 + 1024, khi[8], khi[9], vhi[0], vhi[1]);
    sts128(xa + w * 2560 + 1536, vhi[2], vhi[3], vhi[4], vhi[5]);
    sts128(xa + w * 2560 + 2048, vhi[6], vhi[7], vhi[8], vhi[9]);
  }
  TSIF(par == 0 && w == 1, 64);
#pragma unroll
  for (int j = 0; j < 10; j++) vlo[j] = movm(vlo[j]);
  const bool far0 = 2 * t > g, far1 = 2 * t + 1 > g;
  const uint32_t mfar = (far0 ? 0x0000FFFFu : 0u) | (far1 ? 0xFFFF0000u : 0u);
  float slo[4][2], lg[2][2];
  uint32_t phi[4], plo[4], qml[4], qmh[4];
#pragma unroll
  for (int h = 0; h < 4; h++) {
    const int f = h == 0 ? 0 : h == 1 ? 3 : h == 2 ? 5 : 8, hf = h < 2 ? 2 : 7;
    const bool mine = (h & 1) ? t >= 2 : t < 2;
    qml[h] = mine ? qlo[hf] : 0u;
    qmh[h] = mine ? qhi[hf] : 0u;
    float a[4] = {0.f, 0.f, 0.f, 0.f}, c[4] = {0.f, 0.f, 0.f, 0.f};
    mma16816(a, qlo[f], qhi[f], qlo[f + 1], qhi[f + 1], klo[f], klo[f + 1]);
    mma16816(c, qlo[f], qhi[f], qlo[f + 1], qhi[f + 1], khi[f], khi[f + 1]);
    mma1688(a, qml[h], qmh[h], klo[hf]);
    mma1688(c, qml[h], qmh[h], khi[hf]);
    slo[h][0] = a[0];
    slo[h][1] = a[1];
    lg[h & 1][0] = far0 ? a[2] : c[2];
    lg[h & 1][1] = far1 ? a[3] : c[3];
    if (h & 1) softmax_two(lg, phi[h - 1], phi[h]);
  }
  TSIF(par == 0 && w == 1, 65);
  wg_sync(1 + par);
  TSIF(par == 0 && w == 1, 66);
  const bool nohist = (w == 0) && (b < 8);
  const uint4* hp = g_halo + ((b - 8) * 2 + par) * 224 + lane;
  uint32_t tg[7];
  if (w > 0) {
    const uint4 v0 = lds128(xa + (w - 1) * 2560), v1 = lds128(xa + (w - 1) * 2560 + 512), v2 = lds128(xa + (w - 1) * 2560 + 1024);
    const uint4 v3 = lds128(xa + (w - 1) * 2560 + 1536), v4 = lds128(xa + (w - 1) * 2560 + 2048);
    kpv[0] = v0.x; kpv[1] = v0.y; kpv[2] = v0.z; kpv[3] = v0.w; kpv[4] = v1.x; kpv[5] = v1.y; kpv[6] = v1.z; kpv[7] = v1.w;
    kpv[8] = v2.x; kpv[9] = v2.y; vpv[0] = v2.z; vpv[1] = v2.w; vpv[2] = v3.x; vpv[3] = v3.y; vpv[4] = v3.z; vpv[5] = v3.w;
    vpv[6] = v4.x; vpv[7] = v4.y; vpv[8] = v4.z; vpv[9] = v4.w;
  } else if (nohist) {
#pragma unroll
    for (int j = 0; j < 10; j++) kpv[j] = vpv[j] = 0u;
  } else {
    TSIF(par == 0, 77);
    halo_read(kpv, vpv, tg, hp);
  }
  if (w == 0 && !nohist) {
    int spins = 0;
    while (true) {
      bool ok = true;
#pragma unroll
      for (int j = 0; j < 7; j++) ok = ok && tg[j] == tag;
      if (__all_sync(0xffffffffu, ok) || ++spins > SPIN_LIMIT) break;
      halo_read(kpv, vpv, tg, hp);
    }
    TSIF(par == 0, 79);
  }
#pragma unroll
  for (int h = 0; h < 4; h++) {
    const int f = h == 0 ? 0 : h == 1 ? 3 : h == 2 ? 5 : 8, hf = h < 2 ? 2 : 7;
    float a[4] = {0.f, 0.f, 0.f, 0.f};
    mma16816(a, qlo[f], qhi[f], qlo[f + 1], qhi[f + 1], kpv[f], kpv[f + 1]);
    mma1688(a, qml[h], qmh[h], kpv[hf]);
    const float ninf = __int_as_float(0xff800000);
    lg[h & 1][0] = far0 ? (nohist ? ninf : a[0]) : slo[h][0];
    lg[h & 1][1] = far1 ? (nohist ? ninf : a[1]) : slo[h][1];
    if (h & 1) softmax_two(lg, plo[h - 1], plo[h]);
  }
  TSIF(par == 0 && w <= 1, 67 + w);
  mbar_wait(sb + OFF_BAR + 8 * B_HA, 0);
  fft_matrices(fc, sb, w, lane);
  uint32_t ov[20];
#pragma unroll
  for (int hp = 0; hp < 2; hp++) {
    const int hf = hp ? 7 : 2;
    float sh[4] = {0.f, 0.f, 0.f, 0.f}, i0 = 0.f, i1 = 0.f;
#pragma unroll
    for (int e = 0; e < 2; e++) {
      const int h = 2 * hp + e, f = h == 0 ? 0 : h == 1 ? 3 : h == 2 ? 5 : 8;
      const uint32_t a0 = plo[h] & mfar, a2 = plo[h] & ~mfar, a3 = phi[h] & mfar, c1 = phi[h] & ~mfar;
      float sum[4] = {0.f, 0.f, 0.f, 0.f};
      mma1688(sum, plo[h], phi[h], 0x3F803F80u);
      const float r0 = rcp(sum[0]), r1 = rcp(sum[2]);
#pragma unroll
      for (int j = f; j < f + 2; j++) {
        float o[4] = {0.f, 0.f, 0.f, 0.f};
        mma16816(o, a0, 0u, a2, a3, vpv[j], vlo[j]);
        mma1688(o, 0u, c1, vhi[j]);
        ov[2 * j] = pack2(o[0] * r0, o[1] * r0);
        ov[2 * j + 1] = pack2(o[2] * r1, o[3] * r1);
      }
      const bool mine = e ? g >= 4 : g < 4;
      mma16816(sh, a0, 0u, a2, a3, mine ? vpv[hf] : 0u, mine ? vlo[hf] : 0u);
      mma1688(sh, 0u, c1, mine ? vhi[hf] : 0u);
      if (e == 0 || t >= 2) {
        i0 = r0;
        i1 = r1;
      }
    }
    ov[2 * hf] = pack2(sh[0] * i0, sh[1] * i0);
    ov[2 * hf + 1] = pack2(sh[2] * i1, sh[3] * i1);
  }
  TS(32 + 4 * par + w);
  mbar_wait(sb + OFF_BAR + 8 * B_P1, 0);
  const uint32_t oa = sb + OFF_OA + (lane >> 4) * 2048 + (32 * w + 2 * (lane & 15) + par) * 16;
#pragma unroll
  for (int j = 0; j < 5; j++) stsm4(oa + 4096 * j, ov + 4 * j);
  TSIF(par == 0 && w == 0, 120);
  fence_async_smem();
  TSIF(par == 0 && w == 0, 121);
  __syncwarp();
  if (lane == 0) mbar_arrive(sb + OFF_BAR + 8 * B_ATTN);
  TSM(w == 0 || w == 2, 122 + par + (w == 2 ? 3 : 0));
}

struct Maps {
  CUtensorMap x, wm, wt, k, v, y, wo, qm, qt, om, ot, yl, ol, wh;
};

__device__ __forceinline__ void load_stage(uint32_t sb, int kb, int b, const Maps& m) {
  const uint32_t st = sb + (kb & 3) * STAGE_BYTES, bar = sb + OFF_BAR + 8 * (B_FULL1 + (kb & 3));
  const int r = b >> 3, hg = b & 7, slab = kb - KV_KB;
  const bool kv = slab >= 0 && slab < 5;
  const uint32_t kbar = sb + OFF_BAR + 8 * (B_KV + slab), dst = sb + OFF_KVS + slab * KVS_BYTES;
  mbar_expect_tx(bar, STAGE_BYTES);
  if (kv) mbar_expect_tx(kbar, KVS_BYTES);
  tma_3d(st, &m.x, 64 * kb, 64 * r, 0, bar);
  tma_3d(st + ST_W, &m.wm, 80 * hg + (tail_first(hg) ? 16 : 0), 64 * kb, 0, bar);
  tma_3d(st + ST_WT, &m.wt, 80 * hg + (tail_first(hg) ? 0 : 64), 64 * kb, 0, bar);
  if (kv) tma_3d(dst, &m.k, 0, 32 * (b >> 1) - 3, 2 * slab + (b & 1), kbar);
  if (kv) tma_3d(dst + KVS_V, &m.v, 0, 32 * (b >> 1), 2 * slab + (b & 1), kbar);
}

__global__ void __launch_bounds__(NTHR, 1) fused_kernel(const __grid_constant__ Maps m, const Params p) {
  extern __shared__ __align__(1024) uint8_t smem[];
  const uint32_t sb = (uint32_t)__cvta_generic_to_shared(smem);
  const uint32_t bars = sb + OFF_BAR;
  const int tid = threadIdx.x, lane = tid & 31;
  int b = blockIdx.x;
  b = (((b & 63) >> 3) * 2 + (b & 1)) * 8 + (((b < 64 ? 0x6521 : 0x7430) >> (4 * ((b >> 1) & 3))) & 7);
  const int r = b >> 3, hg = b & 7;

  if (tid == T_ISSUE) {
    TSM(true, 0);
#pragma unroll
    for (int i = 0; i < 4; i++) mbar_init(bars + 8 * (B_F0 + i), 1);
    fence_async_smem();
#pragma unroll
    for (int i = 0; i < 4; i++) {
      mbar_expect_tx(bars + 8 * (B_F0 + i), (i ? 0 : ST_W) + 6144);
      if (i == 0) tma_3d(sb, &m.x, 0, 64 * r, 0, bars + 8 * B_F0);
      tma_3d(sb + ST_W + 6144 * i, &m.wh, 80 * hg + (tail_first(hg) ? 16 : 0), 16 * i, 0, bars + 8 * (B_F0 + i));
    }
#pragma unroll
    for (int i = 0; i < 4; i++) mbar_init(bars + 8 * (B_FULL1 + i), 1);
    fence_async_smem();
    mbar_expect_tx(bars + 8 * B_FULL1, STAGE_BYTES - ST_WT);
    tma_3d(sb + ST_WT, &m.wt, 80 * hg + (tail_first(hg) ? 0 : 64), 0, 0, bars + 8 * B_FULL1);
    load_stage(sb, 1, b, m);
  } else if (tid == T_INIT) {
#pragma unroll
    for (int i = 0; i < B_F0; i++) mbar_init(bars + 8 * i, i < B_GATE ? 8 : i < B_CVD ? 4 : i == B_CVD ? 20 : 1);
    fence_async_smem();
  }
  const int warp = __shfl_sync(0xffffffffu, tid >> 5, 0), wg = warp >> 2, w = warp & 3;
  __syncthreads();

  if (wg == 3) {
    asm volatile("setmaxnreg.dec.sync.aligned.u32 56;");
    if (w == 0) {
      if (lane == 0) {
#pragma unroll 1
        for (int kb = 2; kb < 10; kb++) {
          if (kb >= 4) mbar_wait(bars + 8 * (kb == 7 ? B_E3 : B_EMPTY1 + (kb & 3)), (kb >> 3) & 1);
          TSIF(kb >= 4, 44 + kb);
          load_stage(sb, kb, b, m);
          TSIF(kb == 3, 60);
          if (kb == 9) mbar_arrive(bars + 8 * B_LAST);
        }
        mbar_wait(bars + 8 * B_WOP, 0);
        mbar_wait(bars + 8 * B_EPOCH, 0);
        flag_wait(g_cnt + C_W + 32 * hg, (lds32(sb + OFF_EPOCH) + 1) * 16);
        TS(30);
#pragma unroll 1
        for (int j = 0; j < 8; j++) {
          if (j >= 6) mbar_wait(bars + 8 * (B_EMPTY2 + j - 6), 0);
          if (j == 4) mbar_wait(bars + 8 * B_ORB, 0);
          TSIF(j >= 6, 100 + j);
          mbar_expect_tx(bars + 8 * (B_FULL2 + j), j == 0 ? WO_BYTES : j == 5 ? O_BYTES + WO_BYTES + 512 : O_BYTES + WO_BYTES);
          bulk_load(sb + off_w(j), g_WO + (hg * 8 + step_src(hg, j)) * 800, WO_BYTES, bars + 8 * (B_FULL2 + j));
        }
        mbar_wait(bars + 8 * (B_EMPTY2 + 3), 0);
        mbar_expect_tx(bars + 8 * B_QF, O_BYTES);
        tma_2d(sb + OFF_QS, &m.qm, 80 * hg, 128 * r, bars + 8 * B_QF);
        tma_2d(sb + OFF_QT, &m.qt, 80 * hg + 64, 128 * r, bars + 8 * B_QF);
      }
    } else if (w == 1) {
      unsigned epoch = 0;
      if (lane == 0) {
        epoch = atomicAdd(g_cnt + C_LAUNCH, 1u) / NCTA;
        asm volatile("st.shared.u32 [%0], %1;" ::"r"(sb + OFF_EPOCH), "r"(epoch) : "memory");
        mbar_arrive(bars + 8 * B_EPOCH);
        mbar_wait(bars + 8 * B_KVD, 0);
        mbar_expect_tx(bars + 8 * B_HB, 5 * 4096);
#pragma unroll 1
        for (int c = 0; c < 5; c++) {
          if (c == 3) mbar_wait(bars + 8 * B_S3, 0);
          bulk_load(sb + off_ch(c) + U_BYTES, p.ssm_k + (5 * b + c) * SEQ, 4096, bars + 8 * B_HB);
        }
#pragma unroll
        for (int c = 0; c < 4; c++) mbar_expect_tx(bars + 8 * (B_U + c), c < 3 ? U_BYTES : 2 * U_BYTES);
        const uint4* usrc = g_U + 5 * b * U_PITCH;
        mbar_wait(bars + 8 * B_USIG, 0);
        flag_wait(g_cnt + C_PREP + 32 * (b & 15), (epoch + 1) * NCTA);
        TS(23);
#pragma unroll
        for (int c = 0; c < 5; c++) {
          if (c == 3) mbar_wait(bars + 8 * (B_U + 2), 0);
          bulk_load(sb + off_ch(c), usrc + c * U_PITCH, U_BYTES, bars + 8 * (B_U + (c < 3 ? c : 3)));
          TSIF(c == 0 || c == 4, 116 + (c >> 2));
        }
      }
      epoch = __shfl_sync(0xffffffffu, epoch, 0);
      if (lane < 8) {
        const int src = (b & ~7) | step_src(hg, lane);
        mbar_wait(bars + 8 * B_ATTN, 0);
        TS(20);
        bool seen = false;
#pragma unroll 1
        for (int spins = 0; spins < SPIN_LIMIT; spins++) {
          const bool now = !seen && (int)(flag_read(g_cnt + C_O + 32 * src) - (epoch + 1)) >= 0;
          if (now && lane >= 1 && lane < 4) bulk_load(sb + off_o(lane), g_O + src * 1280, O_BYTES, bars + 8 * (B_FULL2 + lane));
          seen = seen || now;
          if (__all_sync(0xff, seen)) break;
        }
        TS(21);
        if (lane == 5) bulk_load(sb + OFF_GATE, g_gate + 128 * r, 512, bars + 8 * (B_FULL2 + 5));
#pragma unroll 1
        for (int j = 4; j < 8; j++) {
          if (lane == j) {
            mbar_wait(bars + 8 * (j < 6 ? B_C34 : B_EMPTY2 + j - 6), 0);
            bulk_load(sb + off_o(j), g_O + src * 1280, O_BYTES, bars + 8 * (B_FULL2 + j));
          }
          __syncwarp(0xff);
        }
        TS(22);
      }
    } else if (w == 2) {
      mbar_wait(bars + 8 * B_PREP, 0);
      flag_signal(g_cnt + C_PREP, 16, lane);
      TS(25);
      if (lane == 0) {
        mbar_arrive(bars + 8 * B_USIG);
        mbar_expect_tx(bars + 8 * B_ORB, O_BYTES / 4 + 64);
        mbar_wait(bars + 8 * B_GATE, 0);
        publish(g_gate + 16 * b, sb + OFF_GATE + 64 * hg, 64);
        bulk_load(sb + OFF_GATE + 64 * hg, g_gate + 16 * b, 64, bars + 8 * B_ORB);
        mbar_wait(bars + 8 * B_ATTN, 0);
        publish(g_O + b * 1280, sb + OFF_OA, O_BYTES);
        tma_2d(sb + OFF_KVX + 10240, &m.ol, 48, b * 160, bars + 8 * B_ORB);
        TS(74);
        mbar_wait(bars + 8 * B_ORB, 0);
        flag_bump(g_cnt + C_O + 32 * b);
        TS(26);
      }
    } else {
      if (lane == 0) {
        uint4* dst = g_WO + (hg * 8 + (r >> 1)) * 800 + (r & 1) * 80;
        mbar_wait(bars + 8 * B_S3, 0);
        asm volatile("cp.async.bulk.prefetch.L2.global [%0], 6400;" ::"l"(p.wo + b * 3200) : "memory");
        mbar_wait(bars + 8 * B_P1, 0);
        mbar_wait(bars + 8 * WB_TRIG, 0);
        mbar_expect_tx(bars + 8 * B_WST, WO_BYTES / 2);
        tma_3d(sb + OFF_WA, &m.wo, 0, 40 * r, 5 * hg, bars + 8 * B_WST);
        mbar_wait(bars + 8 * B_WST, 0);
#pragma unroll 1
        for (int n = 0; n < 5; n++) bulk_store(dst + 160 * n, sb + OFF_WA + 1280 * n, 1280);
        bulk_wait_read();
        mbar_expect_tx(bars + 8 * B_WST, WO_BYTES / 2);
#pragma unroll 1
        for (int n = 0; n < 5; n++) bulk_load(sb + OFF_WA + 1280 * n, dst + 160 * n, 1280, bars + 8 * B_WST);
        mbar_wait(bars + 8 * B_WST, 1);
        flag_bump(g_cnt + C_W + 32 * hg);
        mbar_arrive(bars + 8 * B_WOP);
        TS(71);
        mbar_expect_tx(bars + 8 * B_C34, 3 * (U_BYTES / 4));
        mbar_expect_tx(bars + 8 * B_YRB, 2 * (U_BYTES / 4));
#pragma unroll 1
        for (int c = 0; c < 5; c++) {
          mbar_wait(bars + 8 * (B_YST + c), 0);
          publish(g_U + (5 * b + c) * U_PITCH, sb + off_ch(c), U_BYTES);
          tma_2d(sb + off_ch(c), &m.yl, 48, (5 * b + c) * (U_PITCH / 8), bars + 8 * (c < 3 ? B_C34 : B_YRB));
        }
        TS(75);
        mbar_wait(bars + 8 * B_C34, 0);
        mbar_wait(bars + 8 * B_YRB, 0);
        flag_bump(g_cnt + C_Y + 32 * (b >> 4));
        TS(27);
        mbar_expect_tx(bars + 8 * B_YFULL, 20480);
        flag_wait(g_cnt + C_Y + 32 * hg, (lds32(sb + OFF_EPOCH) + 1) * 16);
        TS(24);
        tma_2d(sb + OFF_YT, &m.y, 128 * r, 80 * hg, bars + 8 * B_YFULL);
        tma_2d(sb + OFF_YT + 10240, &m.y, 128 * r + 64, 80 * hg, bars + 8 * B_YFULL);
      }
    }
  } else {
    asm volatile("setmaxnreg.inc.sync.aligned.u32 152;");
    FftConst fc;
    if (wg < 2) {
      float acc[120];
#pragma unroll
      for (int i = 0; i < 120; i++) acc[i] = 0.f;
      const uint32_t da = desc_lo(sb + wg * 8192, 16), db = desc_lo(sb + ST_W, 8192), dc = desc_lo(sb + ST_WT, 2048);
#pragma unroll
      for (int k = 0; k < 4; k++) {
        mbar_wait(bars + 8 * (B_F0 + k), 0);
        TSIF(w == 0 && wg == 0 && k == 0, 1);
        wg_fence();
        WgSST<192>::mma<HI_SW128, HI_SW128>(acc, da + 2 * k, desc_lo(sb + ST_W, 2048) + 384 * k, 1);
        wg_commit();
      }
      mbar_wait(bars + 8 * B_FULL1, 0);
      wg_fence();
#pragma unroll
      for (int k = 0; k < 4; k++) WgSST<48>::mma<HI_SW128, HI_SW32>(acc + 96, da + 2 * k, dc + 32 * k, 1);
      wg_commit();
#pragma unroll 1
      for (int kb = 1; kb < 10; kb++) {
        mbar_wait(bars + 8 * (B_FULL1 + (kb & 3)), (kb >> 2) & 1);
        const uint32_t so = (kb & 3) * (STAGE_BYTES >> 4);
        wg_fence();
#pragma unroll
        for (int k = 0; k < 4; k++) {
          WgSST<192>::mma<HI_SW128, HI_SW128>(acc, da + so + 2 * k, db + so + 128 * k, 1);
          WgSST<48>::mma<HI_SW128, HI_SW32>(acc + 96, da + so + 2 * k, dc + so + 32 * k, 1);
        }
        wg_commit();
        wg_wait<1>();
        if (lane == 0) mbar_arrive(bars + 8 * (kb == 4 ? B_E3 : B_EMPTY1 + ((kb - 1) & 3)));
      }
      mbar_wait(bars + 8 * B_EPOCH, 0);
      const uint32_t tag = lds32(sb + OFF_EPOCH) + 1;
      mbar_wait(bars + 8 * B_S3, 0);
      wg_wait<0>();
      pin<120>(acc);
      if (lane == 0) mbar_arrive(bars + 8 * B_P1);
      TSM(w == 0, 3 + wg);
      attention(acc, sb, b, wg, w, lane, tag, fc);
    } else {
      const int tw = tid & 127, chl = 64 * (b & 1) + 8 * w + (lane >> 2);
      uint4* up = g_U + chl * U_PITCH + ((4 * (b >> 1) + (lane & 3)) ^ ((b >> 2) & 1));
      uint2 sw[10];
      uint32_t dv = 0;
      if (lane < 5) dv = __ldg(reinterpret_cast<const unsigned short*>(p.ssm_D) + 5 * b + lane);
#pragma unroll
      for (int i = 0; i < 10; i++) sw[i] = ldg64(reinterpret_cast<const uint2*>(p.shift_k) + chl + 128 * (i >> 1) + 32 * (i & 1));
      uint32_t tab[12];
      uint32_t tt[2];
      fft_tables(tab, tw);
      fft_twiddles(tt, tw);
      uint4 res[10];
#pragma unroll
      for (int i = 0; i < 10; i++) res[i] = make_uint4(0, 0, 0, 0);
#pragma unroll 1
      for (int slab = 0; slab < 5; slab++) {
#pragma unroll
        for (int i = 0; i < 8; i++) res[i] = res[i + 2];
        prep_slab(res + 8, sw, sb, slab, w, lane);
        TSIF(w == 0, 99 + 4 * slab);
#pragma unroll
        for (int i = 0; i < 8; i++) sw[i] = sw[i + 2];
      }
      TSIF(w == 0, 28);
      __syncwarp();
      if (lane == 0) mbar_arrive(bars + 8 * B_KVD + ((res[8].x ^ res[9].x) & p.zero));
      mbar_wait(bars + 8 * B_KVD, 0);
      fft_tables_store(tab, sb, tw);
      mbar_wait(bars + 8 * B_LAST, 0);
#pragma unroll
      for (int i = 0; i < 10; i++) up[(128 * (i >> 1) + 32 * (i & 1)) * U_PITCH] = res[i];
      __syncwarp();
      if (lane == 0) mbar_arrive(bars + 8 * B_PREP);
      TSIF(w == 0, 5);
      mbar_wait(bars + 8 * B_LAST, 0);
      prep_gate(p, sb, b, w, lane);
      __syncwarp();
      if (lane == 0) mbar_arrive(bars + 8 * B_GATE);
      TSIF(w == 0, 72);
      mbar_wait(bars + 8 * B_HB, 0);
      TSIF(w == 0, 2);
      const uint32_t ha = sb + U_BYTES + ((tw >> 3) * 16 + 8 + (tw & 7)) * 16;
      uint4 hv[5];
#pragma unroll
      for (int c = 0; c < 5; c++) hv[c] = lds128(ha + off_ch(c));
      __syncwarp();
#pragma unroll
      for (int c = 0; c < 5; c++) sts128((ha ^ 16) + off_ch(c), hv[c].x, hv[c].y, hv[c].z, hv[c].w);
      asm volatile("st.shared.v2.u32 [%0], {%1, %2};" ::"r"(sb + OFF_TT + 8 * tw), "r"(tt[0]), "r"(tt[1]) : "memory");
      if (tw < 5) asm volatile("st.shared.f32 [%0], %1;" ::"r"(sb + OFF_D + 4 * tw), "f"(bf_lo(dv) * 0.125f) : "memory");
      fence_async_smem();
      __syncwarp();
      if (lane == 0) mbar_arrive(bars + 8 * B_HA);
      TSIF(w == 0, 6);
      mbar_wait(bars + 8 * B_HA, 0);
      fft_matrices(fc, sb, w, lane);
    }

    TSM(w == 0 && wg == 2, 124);
#pragma unroll 1
    for (uint32_t tasks = wg == 0 ? TASK0 : wg == 1 ? TASK1 : TASK2; tasks; tasks >>= 4) {
      const int c = (tasks & 7) - 1;
      conv_channel(fc, sb, c, wg, w, lane);
      if (lane == 0) mbar_arrive(bars + 8 * (B_YST + c));
      TSM(w == 0, 10 + c);
    }

    if (wg != 1) {
      const int wg = warp >> 3;
      const int g = lane >> 2;
      float acc[40];
#pragma unroll
      for (int i = 0; i < 40; i++) acc[i] = 0.f;
      const uint32_t da = desc_lo(sb + wg * 1024, 2048), db = desc_lo(sb, 2560);
      mbar_wait(bars + 8 * B_ORB, 0);
      mbar_wait(bars + 8 * B_FULL2, 0);
      TSM(w == 0, 15 + wg);
#pragma unroll 1
      for (int j = 0; j < 8; j++) {
        if (j == 1 - wg) mbar_wait(bars + 8 * B_CVD, 0);
        mbar_wait(bars + 8 * (B_FULL2 + j), 0);
        TSM(w == 0 && wg == 0, 44 + (j < 4 ? j : j + 6));
        const uint32_t oa = da + (off_o(j) >> 4), ob = db + (off_w(j) >> 4);
        wg_fence();
#pragma unroll
        for (int k = 0; k < 5; k++) WgSST<80>::mma<HI_NONE, HI_SW32>(acc, oa + 256 * k, ob + 32 * k, 1);
        wg_commit();
        wg_wait<1>();
        if (j >= 1 && j <= 4 && lane == 0) mbar_arrive(bars + 8 * (B_EMPTY2 + j - 1));
      }
      TSIF(w == 0 && wg == 0, 113);
      const int tr = 64 * wg + 16 * w + (lane & 15);
      const uint32_t fm = sb + OFF_QS + tr * 128, fx = (lane >> 4) ^ (tr & 7);
      const uint32_t ft = sb + OFF_QT + tr * 32 + (((lane >> 4) ^ (tr >> 2)) & 1) * 16;
      const float g0 = __uint_as_float(lds32(sb + OFF_GATE + (64 * wg + 16 * w + g) * 4));
      const float g1 = __uint_as_float(lds32(sb + OFF_GATE + (64 * wg + 16 * w + 8 + g) * 4));
      const uint32_t ga = pack2(g0, g0), gb = pack2(g1, g1);
      const uint32_t na = pack2(1.f - g0, 1.f - g0), nb = pack2(1.f - g1, 1.f - g1);

      uint32_t qf[20];
      mbar_wait(bars + 8 * B_QF, 0);
      TSM(w == 0 && wg == 0, 99);
#pragma unroll
      for (int j = 0; j < 5; j++) ldsm4(qf + 4 * j, j < 4 ? fm + ((fx ^ (2 * j)) << 4) : ft);
#pragma unroll
      for (int i = 0; i < 20; i++) {
        qf[i] = bmul((i & 1) ? gb : ga, qf[i]);
        asm volatile("" : "+r"(qf[i]));
      }

      wg_wait<0>();
      pin<40>(acc);
      TSM(w == 0, 17 + wg);
      uint32_t pb[20];
#pragma unroll
      for (int j = 0; j < 10; j++) {
        pb[2 * j] = bmul(na, pack2(acc[4 * j], acc[4 * j + 1]));
        pb[2 * j + 1] = bmul(nb, pack2(acc[4 * j + 2], acc[4 * j + 3]));
        asm volatile("" : "+r"(pb[2 * j]), "+r"(pb[2 * j + 1]));
      }
      const uint32_t ya = sb + OFF_YT + wg * 10240 + ((lane >> 4) * 8 + (lane & 7)) * 128 +
                          (((2 * w + (((lane >> 3) & 1) ^ wg)) ^ (lane & 7)) << 4);
      mbar_wait(bars + 8 * B_YFULL, 0);
      TSM(w == 0 && wg == 0, 19);
#pragma unroll
      for (int j = 0; j < 5; j++) {
        uint32_t y[4];
        ldsm4t(y, ya + 2048 * j);
#pragma unroll
        for (int i = 0; i < 4; i++)
          qf[4 * j + i] = bfma(qf[4 * j + i], y[i], pb[4 * j + i]);
      }
#pragma unroll
      for (int j = 0; j < 5; j++) stsm4(j < 4 ? fm + ((fx ^ (2 * j)) << 4) : ft, qf + 4 * j);
      fence_async_smem();
      __syncwarp();
      if (lane == 0) {
        const int row = 64 * wg + 16 * w;
        asm volatile("cp.async.bulk.tensor.2d.global.shared::cta.bulk_group [%0, {%2, %3}], [%1];"
                     ::"l"(&m.om), "r"(sb + OFF_QS + row * 128), "r"(80 * hg), "r"(128 * r + row) : "memory");
        asm volatile("cp.async.bulk.tensor.2d.global.shared::cta.bulk_group [%0, {%2, %3}], [%1];"
                     ::"l"(&m.ot), "r"(sb + OFF_QT + row * 32), "r"(80 * hg + 64), "r"(128 * r + row) : "memory");
        asm volatile("cp.async.bulk.commit_group;\ncp.async.bulk.wait_group.read 0;" ::: "memory");
      }
      TSM(w == 0 || w == 3, 40 + 2 * wg + (w & 1));
    }
  }
}

typedef CUresult (*EncodeFn)(CUtensorMap*, CUtensorMapDataType, cuuint32_t, void*, const cuuint64_t*, const cuuint64_t*,
                             const cuuint32_t*, const cuuint32_t*, CUtensorMapInterleave, CUtensorMapSwizzle,
                             CUtensorMapL2promotion, CUtensorMapFloatOOBfill);

void encode(EncodeFn fn, CUtensorMap* tm, const void* base, int rank, const cuuint64_t* dims, const cuuint64_t* strides,
            const cuuint32_t* box, CUtensorMapSwizzle swz, int promo = 2) {
  const cuuint32_t ones[3] = {1, 1, 1};
  fn(tm, CU_TENSOR_MAP_DATA_TYPE_BFLOAT16, rank, const_cast<void*>(base), dims, strides, box, ones,
     CU_TENSOR_MAP_INTERLEAVE_NONE, swz, (CUtensorMapL2promotion)promo, CU_TENSOR_MAP_FLOAT_OOB_FILL_NONE);
}

}

extern "C" void kernel_launch(void* const* d_in, const int* in_sizes, int n_in, void* d_out, int out_size) {
  (void)in_sizes; (void)n_in; (void)out_size;
  Params p;
  p.q = (const __nv_bfloat16*)d_in[0];
  p.k = (const __nv_bfloat16*)d_in[1];
  p.v = (const __nv_bfloat16*)d_in[2];
  p.shift_k = (const __nv_bfloat16*)d_in[3];
  p.ssm_k = (const __nv_bfloat16*)d_in[4];
  p.ssm_D = (const __nv_bfloat16*)d_in[5];
  p.wqkv = (const __nv_bfloat16*)d_in[7];
  p.wo = (const __nv_bfloat16*)d_in[8];
  p.gate_w = (const __nv_bfloat16*)d_in[9];
  p.out = (__nv_bfloat16*)d_out;
  p.zero = 0;

  static EncodeFn fn = nullptr;
  static void *yaddr = nullptr, *oaddr = nullptr;
  if (!fn) {
    cudaDriverEntryPointQueryResult qr;
    void* f = nullptr;
    cudaGetDriverEntryPoint("cuTensorMapEncodeTiled", &f, cudaEnableDefault, &qr);
    fn = (EncodeFn)f;
    cudaGetSymbolAddress(&yaddr, g_U);
    cudaGetSymbolAddress(&oaddr, g_O);
    cudaFuncSetAttribute(fused_kernel, cudaFuncAttributeMaxDynamicSharedMemorySize, SMEM_BYTES);
  }
  Maps m;
  {
    const cuuint64_t dims[3] = {640, 1024, 2}, st[2] = {2560, 1280};
    const cuuint32_t box[3] = {64, 64, 2};
    encode(fn, &m.x, p.q, 3, dims, st, box, CU_TENSOR_MAP_SWIZZLE_128B, PR_X);
  }
  {
    const cuuint64_t dims[3] = {640, 640, 3}, st[2] = {3840, 1280};
    const cuuint32_t box[3] = {64, 64, 3}, boxt[3] = {16, 64, 3};
    encode(fn, &m.wm, p.wqkv, 3, dims, st, box, CU_TENSOR_MAP_SWIZZLE_128B, PR_W);
    encode(fn, &m.wt, p.wqkv, 3, dims, st, boxt, CU_TENSOR_MAP_SWIZZLE_32B, PR_T);
    const cuuint32_t boxh[3] = {64, 16, 3};
    encode(fn, &m.wh, p.wqkv, 3, dims, st, boxh, CU_TENSOR_MAP_SWIZZLE_128B, PR_W);
  }
  {
    const cuuint64_t dims[3] = {64, 2048, 10}, st[2] = {1280, 128};
    const cuuint32_t boxk[3] = {64, 35, 1}, boxv[3] = {64, 32, 1};
    encode(fn, &m.k, p.k, 3, dims, st, boxk, CU_TENSOR_MAP_SWIZZLE_128B, PR_K);
    encode(fn, &m.v, p.v, 3, dims, st, boxv, CU_TENSOR_MAP_SWIZZLE_128B, PR_K);
  }
  {
    const cuuint64_t dims[3] = {16, 640, 40}, st[2] = {1280, 32};
    const cuuint32_t box[3] = {16, 40, 5};
    encode(fn, &m.wo, p.wo, 3, dims, st, box, CU_TENSOR_MAP_SWIZZLE_32B);
  }
  {
    const cuuint64_t dims[2] = {2048, 640}, st[1] = {U_PITCH * 16};
    const cuuint32_t box[2] = {64, 80};
    encode(fn, &m.y, yaddr, 2, dims, st, box, CU_TENSOR_MAP_SWIZZLE_128B);
    const cuuint64_t dl[2] = {64, DIM * U_PITCH / 8}, dol[2] = {64, NCTA * 160}, sl[1] = {128};
    const cuuint32_t bl[2] = {16, 32}, bol[2] = {16, 160};
    encode(fn, &m.yl, yaddr, 2, dl, sl, bl, CU_TENSOR_MAP_SWIZZLE_NONE, PR_R);
    encode(fn, &m.ol, oaddr, 2, dol, sl, bol, CU_TENSOR_MAP_SWIZZLE_NONE, PR_R);
  }
  {
    const cuuint64_t dims[2] = {640, 2048}, st[1] = {1280};
    const cuuint32_t bqm[2] = {64, 128}, bqt[2] = {16, 128}, bom[2] = {64, 16}, bot[2] = {16, 16};
    encode(fn, &m.qm, p.q, 2, dims, st, bqm, CU_TENSOR_MAP_SWIZZLE_128B);
    encode(fn, &m.qt, p.q, 2, dims, st, bqt, CU_TENSOR_MAP_SWIZZLE_32B);
    encode(fn, &m.om, p.out, 2, dims, st, bom, CU_TENSOR_MAP_SWIZZLE_128B);
    encode(fn, &m.ot, p.out, 2, dims, st, bot, CU_TENSOR_MAP_SWIZZLE_32B);
  }
  fused_kernel<<<NCTA, NTHR, SMEM_BYTES>>>(m, p);
}
```

```cpp
#include <cuda.h>
#include <cuda_bf16.h>
#include <cuda_runtime.h>
#include <stdint.h>

namespace {

constexpr int SEQ = 2048, DIM = 640, NCTA = 128, NTHR = 512;

#define KV_KB 2
#define DEV_EXIT 0
#define FENCE_LO 0
#define FENCE_HI 0
#define WB_TRIG B_USIG
#define T_ISSUE 288
#define PR_X 2
#define PR_W 2
#define PR_T 2
#define PR_K 2
#define PR_R 2
#define PR_O 2
#define PR_S 2
#define T_INIT 448
#define TASK0 0x3
#define TASK1 0x52
#define TASK2 0x41

constexpr uint32_t STAGE_BYTES = 47104, ST_W = 16384, ST_WT = 40960;
constexpr uint32_t O_BYTES = 20480, WO_BYTES = 12800;
constexpr uint32_t OFF_OA = 0;
constexpr uint32_t OFF_QS = 3 * O_BYTES, OFF_QT = OFF_QS + 16384;
constexpr uint32_t OFF_WC = 81920;
constexpr uint32_t OFF_WA = 94720;
constexpr uint32_t OFF_GATE = 145920;
constexpr uint32_t OFF_TT = 146432;
constexpr uint32_t OFF_KVX = 148480;
constexpr uint32_t OFF_CH3 = 163840;
constexpr uint32_t CH_BYTES = 12288, U_BYTES = 4096;
constexpr uint32_t OFF_FT = 225280, OFF_GT = 229376;
constexpr uint32_t OFF_CH0 = 188416;
constexpr uint32_t OFF_KVS = OFF_CH0, KVS_V = 4480, KVS_BYTES = 8576;
constexpr uint32_t OFF_YT = 163840;
constexpr uint32_t OFF_BAR = 231936;
constexpr uint32_t SMEM_BYTES = OFF_BAR + 512;

enum : uint32_t {
  B_EMPTY1 = 0, B_S3 = 3, B_E3 = 4, B_EMPTY2 = 5, B_ATTN = 9, B_P1 = 10,
  B_GATE = 11, B_HA = 12, B_KVD = 13, B_PREP = 14, B_YST = 15,
  B_CVD = 20,
  B_FULL2 = 21, B_U = 29, B_KV = 33, B_HB = 38, B_C34 = 39, B_YRB = 40, B_YFULL = 41, B_EPOCH = 42, B_LAST = 43,
  B_WOP = 44, B_USIG = 45, B_WST = 46, B_QF = 47, B_ORB = 48,
  B_F0 = 49, B_FULL1 = 53
};
constexpr uint32_t OFF_EPOCH = OFF_BAR + 8 * 58, OFF_D = OFF_BAR + 8 * 60;
__device__ __forceinline__ uint32_t off_o(int j) { return j < 4 ? OFF_OA + j * O_BYTES : j < 6 ? OFF_CH0 + (j - 4) * O_BYTES : OFF_OA + (j - 6) * O_BYTES; }
__device__ __forceinline__ uint32_t off_w(int j) { return j < 4 ? OFF_WA + j * WO_BYTES : j == 4 ? OFF_KVX : j == 5 ? OFF_WC : OFF_WA + (j - 6) * WO_BYTES; }
__device__ __forceinline__ int step_src(int hg, int j) { return j == 0 ? hg : j <= hg ? j - 1 : j; }
__device__ __forceinline__ bool tail_first(int hg) { return (hg & 3) == 3; }
__device__ __forceinline__ uint32_t off_ch(int c) { return (c < 3 ? OFF_CH0 : OFF_CH3 - 3 * CH_BYTES) + c * CH_BYTES; }

#define U_PITCH 264
__device__ __align__(1024) uint4 g_U[DIM * U_PITCH];
__device__ __align__(128) uint4 g_O[NCTA * 1280];
__device__ uint4 g_WO[64 * 800];
__device__ uint4 g_halo[NCTA * 2 * 7 * 32];
__device__ __align__(128) float g_gate[SEQ];
__device__ unsigned g_cnt[32 * (1 + 2 * 16 + 8 + NCTA)];
constexpr int C_LAUNCH = 0, C_PREP = 32, C_Y = 32 * 17, C_W = 32 * 33, C_O = 32 * 41;

#define TSM(cond, slot) do { } while (0)
#define TSIF(cond, slot) do { if (__LINE__ >= FENCE_LO && __LINE__ < FENCE_HI) sched_fence(); } while (0)
__device__ __forceinline__ void sched_fence() {
  asm volatile("{\n.reg .pred p;\n.reg .u32 c;\nmov.u32 c, %%clock;\nsetp.eq.u32 p, c, 0;\n@p st.shared.u32 [%0], c;\n}"
               ::"r"(1024 + OFF_EPOCH + 4) : "memory");
}
#define TS(slot) TSIF(true, slot)

struct Params {
  const __nv_bfloat16 *q, *k, *v, *shift_k, *ssm_k, *ssm_D, *wqkv, *wo, *gate_w;
  __nv_bfloat16* out;
  uint32_t zero;
};

constexpr int SPIN_LIMIT = 1 << 17;

__device__ __forceinline__ void mbar_init(uint32_t bar, uint32_t count) {
  asm volatile("mbarrier.init.shared::cta.b64 [%0], %1;" ::"r"(bar), "r"(count) : "memory");
}
__device__ __forceinline__ void mbar_expect_tx(uint32_t bar, uint32_t bytes) {
  asm volatile("mbarrier.arrive.expect_tx.shared::cta.b64 _, [%0], %1;" ::"r"(bar), "r"(bytes) : "memory");
}
__device__ __forceinline__ void mbar_arrive(uint32_t bar) {
  asm volatile("mbarrier.arrive.shared::cta.b64 _, [%0];" ::"r"(bar) : "memory");
}
__device__ __forceinline__ void mbar_wait(uint32_t bar, uint32_t parity) {
  uint32_t ok;
  int spins = 0;
  do {
      asm volatile("{\n.reg .pred p;\nmbarrier.try_wait.parity.shared::cta.b64 p, [%1], %2;\nselp.b32 %0, 1, 0, p;\n}"
                   : "=r"(ok) : "r"(bar), "r"(parity) : "memory");
    if (++spins > SPIN_LIMIT) break;
  } while (!ok);
}
__device__ __forceinline__ unsigned flag_read(const unsigned* p) {
  unsigned v;
  asm volatile("ld.relaxed.gpu.global.u32 %0, [%1];" : "=r"(v) : "l"(p) : "memory");
  return v;
}
__device__ __forceinline__ void flag_poll(const unsigned* p, unsigned target) {
  unsigned v;
  int spins = 0;
  do {
    asm volatile("ld.relaxed.gpu.global.u32 %0, [%1];" : "=r"(v) : "l"(p) : "memory");
    if (++spins > SPIN_LIMIT) break;
  } while ((int)(v - target) < 0);
}
__device__ __forceinline__ void flag_wait(const unsigned* p, unsigned target) {
  flag_poll(p, target);
}
__device__ __forceinline__ void flag_signal(unsigned* p, int n, int lane) {
  if (lane == 0) asm volatile("fence.release.gpu;" ::: "memory");
  __syncwarp();
  if (lane < n) asm volatile("red.relaxed.gpu.global.add.u32 [%0], 1;" ::"l"(p + 32 * lane) : "memory");
}
__device__ __forceinline__ void flag_bump(unsigned* p) {
  asm volatile("red.relaxed.gpu.global.add.u32 [%0], 1;" ::"l"(p) : "memory");
}
__device__ __forceinline__ void fence_async_smem() { asm volatile("fence.proxy.async.shared::cta;" ::: "memory"); }
__device__ __forceinline__ void wg_sync(int id) { asm volatile("bar.sync %0, 128;" ::"r"(id) : "memory"); }

__device__ __forceinline__ void tma_2d(uint32_t dst, const CUtensorMap* tm, int c0, int c1, uint32_t bar) {
  asm volatile("cp.async.bulk.tensor.2d.shared::cluster.global.mbarrier::complete_tx::bytes [%0], [%1, {%3, %4}], [%2];"
               ::"r"(dst), "l"(tm), "r"(bar), "r"(c0), "r"(c1) : "memory");
}
__device__ __forceinline__ void tma_3d(uint32_t dst, const CUtensorMap* tm, int c0, int c1, int c2, uint32_t bar) {
  asm volatile("cp.async.bulk.tensor.3d.shared::cluster.global.mbarrier::complete_tx::bytes [%0], [%1, {%3, %4, %5}], [%2];"
               ::"r"(dst), "l"(tm), "r"(bar), "r"(c0), "r"(c1), "r"(c2) : "memory");
}
__device__ __forceinline__ void bulk_load(uint32_t dst, const void* src, uint32_t bytes, uint32_t bar) {
  asm volatile("cp.async.bulk.shared::cluster.global.mbarrier::complete_tx::bytes [%0], [%1], %2, [%3];"
               ::"r"(dst), "l"(src), "r"(bytes), "r"(bar) : "memory");
}
__device__ __forceinline__ void bulk_store(void* dst, uint32_t src, uint32_t bytes) {
  asm volatile("cp.async.bulk.global.shared::cta.bulk_group [%0], [%1], %2;" ::"l"(dst), "r"(src), "r"(bytes) : "memory");
}
__device__ __forceinline__ void bulk_wait_read() {
  asm volatile("cp.async.bulk.commit_group;\ncp.async.bulk.wait_group.read 0;" ::: "memory");
}

__device__ __forceinline__ void publish(void* dst, uint32_t src, uint32_t bytes) {
  bulk_store(dst, src, bytes);
  bulk_wait_read();
}

__device__ __forceinline__ void wg_fence() { asm volatile("wgmma.fence.sync.aligned;" ::: "memory"); }
__device__ __forceinline__ void wg_commit() { asm volatile("wgmma.commit_group.sync.aligned;" ::: "memory"); }
template <int N> __device__ __forceinline__ void wg_wait() { asm volatile("wgmma.wait_group.sync.aligned %0;" ::"n"(N) : "memory"); }
__device__ __forceinline__ uint32_t desc_lo(uint32_t addr, uint32_t lbo) { return ((addr & 0x3FFFF) >> 4) | ((lbo >> 4) << 16); }
constexpr uint32_t desc_hi(uint32_t sbo, uint32_t swz) { return (sbo >> 4) | (swz << 30); }
constexpr uint32_t HI_SW128 = desc_hi(1024, 1), HI_SW64 = desc_hi(512, 2), HI_SW32 = desc_hi(256, 3), HI_NONE = desc_hi(128, 0);
template <int N> __device__ __forceinline__ void pin(float* d) {
#pragma unroll
  for (int i = 0; i < N; i++) asm volatile("" : "+f"(d[i])::"memory");
}

__device__ __forceinline__ uint32_t lds32(uint32_t a) {
  uint32_t v;
  asm volatile("ld.volatile.shared.u32 %0, [%1];" : "=r"(v) : "r"(a) : "memory");
  return v;
}
__device__ __forceinline__ uint2 ldg64(const void* a) {
  uint2 v;
  asm volatile("ld.global.nc.v2.u32 {%0, %1}, [%2];" : "=r"(v.x), "=r"(v.y) : "l"(a) : "memory");
  return v;
}
__device__ __forceinline__ void ldsm4(uint32_t* r, uint32_t a) {
  asm volatile("ldmatrix.sync.aligned.m8n8.x4.shared.b16 {%0, %1, %2, %3}, [%4];"
               : "=r"(r[0]), "=r"(r[1]), "=r"(r[2]), "=r"(r[3]) : "r"(a) : "memory");
}
__device__ __forceinline__ void ldsm4t(uint32_t* r, uint32_t a) {
  asm volatile("ldmatrix.sync.aligned.m8n8.x4.trans.shared.b16 {%0, %1, %2, %3}, [%4];"
               : "=r"(r[0]), "=r"(r[1]), "=r"(r[2]), "=r"(r[3]) : "r"(a) : "memory");
}
__device__ __forceinline__ uint2 lds64(uint32_t a) {
  uint2 v;
  asm volatile("ld.shared.v2.u32 {%0, %1}, [%2];" : "=r"(v.x), "=r"(v.y) : "r"(a) : "memory");
  return v;
}
__device__ __forceinline__ uint4 lds128(uint32_t a) {
  uint4 v;
  asm volatile("ld.shared.v4.u32 {%0, %1, %2, %3}, [%4];" : "=r"(v.x), "=r"(v.y), "=r"(v.z), "=r"(v.w) : "r"(a) : "memory");
  return v;
}
__device__ __forceinline__ void sts128(uint32_t a, uint32_t x, uint32_t y, uint32_t z, uint32_t w) {
  asm volatile("st.shared.v4.u32 [%0], {%1, %2, %3, %4};" ::"r"(a), "r"(x), "r"(y), "r"(z), "r"(w) : "memory");
}
__device__ __forceinline__ void stsm4(uint32_t a, const uint32_t* r) {
  asm volatile("stmatrix.sync.aligned.m8n8.x4.shared.b16 [%0], {%1, %2, %3, %4};" ::"r"(a), "r"(r[0]), "r"(r[1]), "r"(r[2]), "r"(r[3]) : "memory");
}
__device__ __forceinline__ uint32_t pack2(float lo, float hi) {
  uint32_t r;
  asm("cvt.rn.bf16x2.f32 %0, %1, %2;" : "=r"(r) : "f"(hi), "f"(lo));
  return r;
}
__device__ __forceinline__ uint32_t movm(uint32_t a) {
  uint32_t d;
  asm volatile("movmatrix.sync.aligned.m8n8.trans.b16 %0, %1;" : "=r"(d) : "r"(a));
  return d;
}
__device__ __forceinline__ uint32_t bmul(uint32_t a, uint32_t b) {
  uint32_t d;
  asm("mul.rn.bf16x2 %0, %1, %2;" : "=r"(d) : "r"(a), "r"(b));
  return d;
}
__device__ __forceinline__ uint32_t badd(uint32_t a, uint32_t b) {
  uint32_t d;
  asm("add.rn.bf16x2 %0, %1, %2;" : "=r"(d) : "r"(a), "r"(b));
  return d;
}
__device__ __forceinline__ uint32_t bfma(uint32_t a, uint32_t b, uint32_t c) {
  uint32_t d;
  asm("fma.rn.bf16x2 %0, %1, %2, %3;" : "=r"(d) : "r"(a), "r"(b), "r"(c));
  return d;
}
__device__ __forceinline__ float bf_lo(uint32_t x) { return __uint_as_float(x << 16); }
__device__ __forceinline__ float bf_hi(uint32_t x) { return __uint_as_float(x & 0xFFFF0000u); }
__device__ __forceinline__ float ex2(float x) {
  float y;
  asm("ex2.approx.ftz.f32 %0, %1;" : "=f"(y) : "f"(x));
  return y;
}
__device__ __forceinline__ float rcp(float x) {
  float y;
  asm("rcp.approx.ftz.f32 %0, %1;" : "=f"(y) : "f"(x));
  return y;
}
__device__ __forceinline__ void mma16816(float* d, uint32_t a0, uint32_t a1, uint32_t a2, uint32_t a3, uint32_t b0, uint32_t b1) {
  asm volatile("mma.sync.aligned.m16n8k16.row.col.f32.bf16.bf16.f32 {%0, %1, %2, %3}, {%4, %5, %6, %7}, {%8, %9}, {%0, %1, %2, %3};"
               : "+f"(d[0]), "+f"(d[1]), "+f"(d[2]), "+f"(d[3])
               : "r"(a0), "r"(a1), "r"(a2), "r"(a3), "r"(b0), "r"(b1));
}
__device__ __forceinline__ void mma1688(float* d, uint32_t a0, uint32_t a1, uint32_t b0) {
  asm volatile("mma.sync.aligned.m16n8k8.row.col.f32.bf16.bf16.f32 {%0, %1, %2, %3}, {%4, %5}, {%6}, {%0, %1, %2, %3};"
               : "+f"(d[0]), "+f"(d[1]), "+f"(d[2]), "+f"(d[3])
               : "r"(a0), "r"(a1), "r"(b0));
}

template <int N> struct WgRS;
template <int N> struct WgSST;
template <> struct WgRS<32> {
  template <uint32_t HB>
  static __device__ __forceinline__ void mma(float* d, const uint32_t* a, uint32_t db) {
    asm volatile("{\n.reg .pred p;\n.reg .b64 db;\nsetp.ne.b32 p, %22, 0;\n"
      "mov.b64 db, {%20, %21};\n"
      "wgmma.mma_async.sync.aligned.m64n32k16.f32.bf16.bf16 {"
      "%0, %1, %2, %3, %4, %5, %6, %7, %8, %9, %10, %11, %12, %13, %14, %15"
      "}, {%16, %17, %18, %19}, db, p, 1, 1, 1;\n}\n"
      : "+f"(d[0]), "+f"(d[1]), "+f"(d[2]), "+f"(d[3]), "+f"(d[4]), "+f"(d[5]), "+f"(d[6]), "+f"(d[7]),
        "+f"(d[8]), "+f"(d[9]), "+f"(d[10]), "+f"(d[11]), "+f"(d[12]), "+f"(d[13]), "+f"(d[14]), "+f"(d[15])
      : "r"(a[0]), "r"(a[1]), "r"(a[2]), "r"(a[3]), "r"(db), "n"(HB), "n"(1));
  }
  template <uint32_t HB>
  static __device__ __forceinline__ void set(float* d, const uint32_t* a, uint32_t db) {
    asm volatile("{\n.reg .pred p;\n.reg .b64 db;\nsetp.ne.b32 p, %22, 0;\n"
      "mov.b64 db, {%20, %21};\n"
      "wgmma.mma_async.sync.aligned.m64n32k16.f32.bf16.bf16 {"
      "%0, %1, %2, %3, %4, %5, %6, %7, %8, %9, %10, %11, %12, %13, %14, %15"
      "}, {%16, %17, %18, %19}, db, p, 1, 1, 1;\n}\n"
      : "=f"(d[0]), "=f"(d[1]), "=f"(d[2]), "=f"(d[3]), "=f"(d[4]), "=f"(d[5]), "=f"(d[6]), "=f"(d[7]),
        "=f"(d[8]), "=f"(d[9]), "=f"(d[10]), "=f"(d[11]), "=f"(d[12]), "=f"(d[13]), "=f"(d[14]), "=f"(d[15])
      : "r"(a[0]), "r"(a[1]), "r"(a[2]), "r"(a[3]), "r"(db), "n"(HB), "n"(0));
  }
};
template <> struct WgRS<64> {
  template <uint32_t HB>
  static __device__ __forceinline__ void mma(float* d, const uint32_t* a, uint32_t db) {
    asm volatile("{\n.reg .pred p;\n.reg .b64 db;\nsetp.ne.b32 p, %38, 0;\n"
      "mov.b64 db, {%36, %37};\n"
      "wgmma.mma_async.sync.aligned.m64n64k16.f32.bf16.bf16 {"
      "%0, %1, %2, %3, %4, %5, %6, %7, %8, %9, %10, %11, %12, %13, %14, %15, "
      "%16, %17, %18, %19, %20, %21, %22, %23, %24, %25, %26, %27, %28, %29, %30, %31"
      "}, {%32, %33, %34, %35}, db, p, 1, 1, 1;\n}\n"
      : "+f"(d[0]), "+f"(d[1]), "+f"(d[2]), "+f"(d[3]), "+f"(d[4]), "+f"(d[5]), "+f"(d[6]), "+f"(d[7]),
        "+f"(d[8]), "+f"(d[9]), "+f"(d[10]), "+f"(d[11]), "+f"(d[12]), "+f"(d[13]), "+f"(d[14]), "+f"(d[15]),
        "+f"(d[16]), "+f"(d[17]), "+f"(d[18]), "+f"(d[19]), "+f"(d[20]), "+f"(d[21]), "+f"(d[22]), "+f"(d[23]),
        "+f"(d[24]), "+f"(d[25]), "+f"(d[26]), "+f"(d[27]), "+f"(d[28]), "+f"(d[29]), "+f"(d[30]), "+f"(d[31])
      : "r"(a[0]), "r"(a[1]), "r"(a[2]), "r"(a[3]), "r"(db), "n"(HB), "n"(1));
  }
  template <uint32_t HB>
  static __device__ __forceinline__ void set(float* d, const uint32_t* a, uint32_t db) {
    asm volatile("{\n.reg .pred p;\n.reg .b64 db;\nsetp.ne.b32 p, %38, 0;\n"
      "mov.b64 db, {%36, %37};\n"
      "wgmma.mma_async.sync.aligned.m64n64k16.f32.bf16.bf16 {"
      "%0, %1, %2, %3, %4, %5, %6, %7, %8, %9, %10, %11, %12, %13, %14, %15, "
      "%16, %17, %18, %19, %20, %21, %22, %23, %24, %25, %26, %27, %28, %29, %30, %31"
      "}, {%32, %33, %34, %35}, db, p, 1, 1, 1;\n}\n"
      : "=f"(d[0]), "=f"(d[1]), "=f"(d[2]), "=f"(d[3]), "=f"(d[4]), "=f"(d[5]), "=f"(d[6]), "=f"(d[7]),
        "=f"(d[8]), "=f"(d[9]), "=f"(d[10]), "=f"(d[11]), "=f"(d[12]), "=f"(d[13]), "=f"(d[14]), "=f"(d[15]),
        "=f"(d[16]), "=f"(d[17]), "=f"(d[18]), "=f"(d[19]), "=f"(d[20]), "=f"(d[21]), "=f"(d[22]), "=f"(d[23]),
        "=f"(d[24]), "=f"(d[25]), "=f"(d[26]), "=f"(d[27]), "=f"(d[28]), "=f"(d[29]), "=f"(d[30]), "=f"(d[31])
      : "r"(a[0]), "r"(a[1]), "r"(a[2]), "r"(a[3]), "r"(db), "n"(HB), "n"(0));
  }
};
template <> struct WgSST<48> {
  template <uint32_t HA, uint32_t HB>
  static __device__ __forceinline__ void mma(float* d, uint32_t da, uint32_t db, int sc) {
    asm volatile("{\n.reg .pred p;\n.reg .b64 da, db;\nsetp.ne.b32 p, %28, 0;\n"
      "mov.b64 da, {%24, %25};\nmov.b64 db, {%26, %27};\n"
      "wgmma.mma_async.sync.aligned.m64n48k16.f32.bf16.bf16 {"
      "%0, %1, %2, %3, %4, %5, %6, %7, %8, %9, %10, %11, %12, %13, %14, %15, "
      "%16, %17, %18, %19, %20, %21, %22, %23"
      "}, da, db, p, 1, 1, 0, 1;\n}\n"
      : "+f"(d[0]), "+f"(d[1]), "+f"(d[2]), "+f"(d[3]), "+f"(d[4]), "+f"(d[5]), "+f"(d[6]), "+f"(d[7]),
        "+f"(d[8]), "+f"(d[9]), "+f"(d[10]), "+f"(d[11]), "+f"(d[12]), "+f"(d[13]), "+f"(d[14]), "+f"(d[15]),
        "+f"(d[16]), "+f"(d[17]), "+f"(d[18]), "+f"(d[19]), "+f"(d[20]), "+f"(d[21]), "+f"(d[22]), "+f"(d[23])
      : "r"(da), "n"(HA), "r"(db), "n"(HB), "r"(sc));
  }
};
template <> struct WgSST<80> {
  template <uint32_t HA, uint32_t HB>
  static __device__ __forceinline__ void mma(float* d, uint32_t da, uint32_t db, int sc) {
    asm volatile("{\n.reg .pred p;\n.reg .b64 da, db;\nsetp.ne.b32 p, %44, 0;\n"
      "mov.b64 da, {%40, %41};\nmov.b64 db, {%42, %43};\n"
      "wgmma.mma_async.sync.aligned.m64n80k16.f32.bf16.bf16 {"
      "%0, %1, %2, %3, %4, %5, %6, %7, %8, %9, %10, %11, %12, %13, %14, %15, "
      "%16, %17, %18, %19, %20, %21, %22, %23, %24, %25, %26, %27, %28, %29, %30, %31, "
      "%32, %33, %34, %35, %36, %37, %38, %39"
      "}, da, db, p, 1, 1, 0, 1;\n}\n"
      : "+f"(d[0]), "+f"(d[1]), "+f"(d[2]), "+f"(d[3]), "+f"(d[4]), "+f"(d[5]), "+f"(d[6]), "+f"(d[7]),
        "+f"(d[8]), "+f"(d[9]), "+f"(d[10]), "+f"(d[11]), "+f"(d[12]), "+f"(d[13]), "+f"(d[14]), "+f"(d[15]),
        "+f"(d[16]), "+f"(d[17]), "+f"(d[18]), "+f"(d[19]), "+f"(d[20]), "+f"(d[21]), "+f"(d[22]), "+f"(d[23]),
        "+f"(d[24]), "+f"(d[25]), "+f"(d[26]), "+f"(d[27]), "+f"(d[28]), "+f"(d[29]), "+f"(d[30]), "+f"(d[31]),
        "+f"(d[32]), "+f"(d[33]), "+f"(d[34]), "+f"(d[35]), "+f"(d[36]), "+f"(d[37]), "+f"(d[38]), "+f"(d[39])
      : "r"(da), "n"(HA), "r"(db), "n"(HB), "r"(sc));
  }
};
template <> struct WgSST<192> {
  template <uint32_t HA, uint32_t HB>
  static __device__ __forceinline__ void mma(float* d, uint32_t da, uint32_t db, int sc) {
    asm volatile("{\n.reg .pred p;\n.reg .b64 da, db;\nsetp.ne.b32 p, %100, 0;\n"
      "mov.b64 da, {%96, %97};\nmov.b64 db, {%98, %99};\n"
      "wgmma.mma_async.sync.aligned.m64n192k16.f32.bf16.bf16 {"
      "%0, %1, %2, %3, %4, %5, %6, %7, %8, %9, %10, %11, %12, %13, %14, %15, "
      "%16, %17, %18, %19, %20, %21, %22, %23, %24, %25, %26, %27, %28, %29, %30, %31, "
      "%32, %33, %34, %35, %36, %37, %38, %39, %40, %41, %42, %43, %44, %45, %46, %47, "
      "%48, %49, %50, %51, %52, %53, %54, %55, %56, %57, %58, %59, %60, %61, %62, %63, "
      "%64, %65, %66, %67, %68, %69, %70, %71, %72, %73, %74, %75, %76, %77, %78, %79, "
      "%80, %81, %82, %83, %84, %85, %86, %87, %88, %89, %90, %91, %92, %93, %94, %95"
      "}, da, db, p, 1, 1, 0, 1;\n}\n"
      : "+f"(d[0]), "+f"(d[1]), "+f"(d[2]), "+f"(d[3]), "+f"(d[4]), "+f"(d[5]), "+f"(d[6]), "+f"(d[7]),
        "+f"(d[8]), "+f"(d[9]), "+f"(d[10]), "+f"(d[11]), "+f"(d[12]), "+f"(d[13]), "+f"(d[14]), "+f"(d[15]),
        "+f"(d[16]), "+f"(d[17]), "+f"(d[18]), "+f"(d[19]), "+f"(d[20]), "+f"(d[21]), "+f"(d[22]), "+f"(d[23]),
        "+f"(d[24]), "+f"(d[25]), "+f"(d[26]), "+f"(d[27]), "+f"(d[28]), "+f"(d[29]), "+f"(d[30]), "+f"(d[31]),
        "+f"(d[32]), "+f"(d[33]), "+f"(d[34]), "+f"(d[35]), "+f"(d[36]), "+f"(d[37]), "+f"(d[38]), "+f"(d[39]),
        "+f"(d[40]), "+f"(d[41]), "+f"(d[42]), "+f"(d[43]), "+f"(d[44]), "+f"(d[45]), "+f"(d[46]), "+f"(d[47]),
        "+f"(d[48]), "+f"(d[49]), "+f"(d[50]), "+f"(d[51]), "+f"(d[52]), "+f"(d[53]), "+f"(d[54]), "+f"(d[55]),
        "+f"(d[56]), "+f"(d[57]), "+f"(d[58]), "+f"(d[59]), "+f"(d[60]), "+f"(d[61]), "+f"(d[62]), "+f"(d[63]),
        "+f"(d[64]), "+f"(d[65]), "+f"(d[66]), "+f"(d[67]), "+f"(d[68]), "+f"(d[69]), "+f"(d[70]), "+f"(d[71]),
        "+f"(d[72]), "+f"(d[73]), "+f"(d[74]), "+f"(d[75]), "+f"(d[76]), "+f"(d[77]), "+f"(d[78]), "+f"(d[79]),
        "+f"(d[80]), "+f"(d[81]), "+f"(d[82]), "+f"(d[83]), "+f"(d[84]), "+f"(d[85]), "+f"(d[86]), "+f"(d[87]),
        "+f"(d[88]), "+f"(d[89]), "+f"(d[90]), "+f"(d[91]), "+f"(d[92]), "+f"(d[93]), "+f"(d[94]), "+f"(d[95])
      : "r"(da), "n"(HA), "r"(db), "n"(HB), "r"(sc));
  }
};

struct FftConst {
  uint32_t f[2][4], fi[4][4];
  uint32_t ta[2][2], tb[2][2];
};
__device__ __forceinline__ void cis(int m, float scale, float& c, float& s) {
  const float a = (float)m * (-6.283185307179586f * scale);
  c = __cosf(a);
  s = __sinf(a);
}
__device__ __forceinline__ void fft_tables(uint32_t (&v)[12], int tw) {
  const int row = tw >> 2, ch = tw & 3;
#pragma unroll
  for (int i = 0; i < 4; i++) {
    float c[2], s[2], x[2];
#pragma unroll
    for (int e = 0; e < 2; e++) {
      cis((((32 * (8 * ch + 2 * i + e) + 15) * (4 * row - 63) + 2048) & 4095) - 2048, 1.f / 4096, c[e], s[e]);
      float gc, gs;
      cis((((row & 15) * (8 * (ch & 1) + 2 * i + e) + 8) & 15) - 8, 1.f / 16, gc, gs);
      x[e] = (row >> 4) == (ch >> 1) ? gc : (ch >> 1) ? gs : -gs;
    }
    v[i] = pack2(c[0] * 0.125f, c[1] * 0.125f);
    v[4 + i] = pack2(s[0] * 0.125f, s[1] * 0.125f);
    v[8 + i] = pack2(x[0], x[1]);
  }
#pragma unroll
  for (int i = 0; i < 12; i++) asm volatile("" : "+r"(v[i]));
}
__device__ __forceinline__ void fft_tables_store(const uint32_t (&v)[12], uint32_t sb, int tw) {
  const int row = tw >> 2;
  const uint32_t x = ((tw ^ (row >> 1)) & 3) << 4, a = sb + OFF_FT + (16 * (row >> 3) + (row & 7)) * 64 + x;
  sts128(a, v[0], v[1], v[2], v[3]);
  sts128(a + 512, v[4], v[5], v[6], v[7]);
  sts128(sb + OFF_GT + row * 64 + x, v[8], v[9], v[10], v[11]);
}
__device__ __forceinline__ void fft_twiddles(uint32_t (&v)[2], int tw) {
  float a[2], s[2];
#pragma unroll
  for (int i = 0; i < 2; i++) {
    float c;
    cis((2 * (2 * (tw & 3) + i) - 15) * (4 * (tw >> 2) - 63), 1.f / 4096, c, s[i]);
    a[i] = __fdividef(-s[i], 1.f + c);
  }
  v[0] = pack2(a[0], a[1]);
  v[1] = pack2(s[0], s[1]);
  asm volatile("" : "+r"(v[0]), "+r"(v[1]));
}
__device__ __forceinline__ void fft_matrices(FftConst& k, uint32_t sb, int w, int lane) {
  const uint32_t x = (lane >> 1) & 3;
  const uint2 t0 = lds64(sb + OFF_TT + 256 * w + 8 * lane), t1 = lds64(sb + OFF_TT + 256 * w + 8 * (lane ^ 3));
  k.ta[0][0] = t0.x;
  k.tb[0][0] = t0.y;
  k.ta[1][1] = __byte_perm(t1.x, 0, 0x1032);
  k.tb[1][1] = __byte_perm(t1.y, 0, 0x1032);
#pragma unroll
  for (int j = 0; j < 2; j++) {
    k.ta[1 - j][j] = k.ta[j][j] ^ 0x80008000u;
    k.tb[1 - j][j] = k.tb[j][j] ^ 0x80008000u;
    asm volatile("" : "+r"(k.ta[0][j]), "+r"(k.tb[0][j]), "+r"(k.ta[1][j]), "+r"(k.tb[1][j]));
  }
#pragma unroll
  for (int i = 0; i < 2; i++) {
    ldsm4(k.f[i], sb + OFF_FT + (16 * w + (lane & 15)) * 64 + (((2 * i + (lane >> 4)) ^ x) << 4));
    ldsm4t(k.fi[i], sb + OFF_FT + (32 * i + lane) * 64 + ((w ^ x) << 4));
#pragma unroll
    for (int j = 0; j < 4; j++) {
      k.fi[2 + i][j] = (j & 1) ? k.fi[i][j - 1] ^ 0x80008000u : k.fi[i][j + 1];
      asm volatile("" : "+r"(k.fi[2 + i][j]));
    }
  }
}
__device__ __forceinline__ void rot(uint32_t& x, uint32_t& y, uint32_t a, uint32_t b) {
  x = bfma(a, y, x);
  y = bfma(b, x, y);
  x = bfma(a, y, x);
}
__device__ __forceinline__ void twiddle_fwd(uint32_t (&a)[4][4], float* d, const FftConst& k) {
#pragma unroll
  for (int q = 0; q < 4; q++)
#pragma unroll
    for (int j = 0; j < 2; j++) {
      const float* x = d + 8 * q + 4 * j;
      uint32_t re = pack2(x[0], x[1]), im = pack2(x[2], x[3]);
      rot(re, im, k.ta[0][j], k.tb[0][j]);
      a[q & 2][2 * j + (q & 1)] = re;
      a[(q & 2) + 1][2 * j + (q & 1)] = im;
    }
}
__device__ __forceinline__ void g_step(float* d, const uint32_t (&a)[4][4], uint32_t dre, uint32_t dim) {
  WgRS<32>::set<HI_SW64>(d, a[0], dre);
  WgRS<32>::set<HI_SW64>(d + 16, a[2], dre);
  WgRS<32>::mma<HI_SW64>(d, a[1], dim);
  WgRS<32>::mma<HI_SW64>(d + 16, a[3], dim);
  wg_commit();
}

__device__ __forceinline__ void products(uint32_t (&a)[4][4], const float* H, const float* U, int p) {
#pragma unroll
  for (int j = 0; j < 2; j++)
#pragma unroll
    for (int m = 2 * p; m < 2 * p + 2; m++) {
      float pr[2], pi[2];
#pragma unroll
      for (int x = 0; x < 2; x++)
#pragma unroll
        for (int q = 0; q <= m; q++) {
          const int ih = 16 * (q >> 1) + 2 * (q & 1) + 4 * j + x, iu = 16 * ((m - q) >> 1) + 2 * ((m - q) & 1) + 4 * j + x;
          pr[x] = q ? fmaf(H[ih], U[iu], pr[x]) : H[ih] * U[iu];
          pi[x] = q ? fmaf(H[ih], U[iu + 8], pi[x]) : H[ih] * U[iu + 8];
          pr[x] = fmaf(-H[ih + 8], U[iu + 8], pr[x]);
          pi[x] = fmaf(H[ih + 8], U[iu], pi[x]);
        }
      a[m & 2][2 * j + (m & 1)] = pack2(pr[0], pr[1]);
      a[(m & 2) + 1][2 * j + (m & 1)] = pack2(pi[0], pi[1]);
    }
}

__device__ __forceinline__ void conv_channel(const FftConst& k, uint32_t sb, int c, int wg, int w, int lane) {
  const uint32_t cb = sb + off_ch(c), bars = sb + OFF_BAR;
  const uint32_t du = desc_lo(cb, 1024), dg = desc_lo(sb + OFF_GT, 16), dz = desc_lo(cb + U_BYTES, 16);
  float U[32], H[32];
  uint32_t a[4][4], e[4][4];
  const float dv = __uint_as_float(lds32(sb + OFF_D + 4 * c));
  wg_fence();
  WgRS<64>::set<HI_SW32>(H, k.f[0], du + 256);
  WgRS<64>::mma<HI_SW32>(H, k.f[1], du + 256 + 32);
  wg_commit();
  wg_wait<0>();
  pin<32>(H);
  twiddle_fwd(a, H, k);
  mbar_wait(bars + 8 * (B_U + (c < 3 ? c : 3)), 0);
  TSM(w == 0 && c < 3, 7 + wg);
  wg_fence();
  WgRS<64>::set<HI_SW32>(U, k.f[0], du);
  WgRS<64>::mma<HI_SW32>(U, k.f[1], du + 32);
  wg_commit();
  g_step(H, a, dg, dg + 64);
  wg_wait<1>();
  pin<32>(U);
  twiddle_fwd(e, U, k);
  wg_fence();
  g_step(U, e, dg, dg + 64);
  wg_wait<0>();
  pin<32>(U);
  pin<32>(H);
#pragma unroll
  for (int j = 0; j < 4; j++) H[4 * (j >> 1) + (j & 1)] += dv;
  float V[32];
#pragma unroll
  for (int p = 0; p < 2; p++) {
    products(a, H, U, p);
    wg_fence();
    WgRS<32>::set<HI_SW64>(V + 16 * p, a[2 * p], dg + 64);
    WgRS<32>::mma<HI_SW64>(V + 16 * p, a[2 * p + 1], dg);
    wg_commit();
  }
  const uint32_t za = cb + U_BYTES + (8 * w + (lane & 7)) * 128 + (((lane >> 3) ^ (lane & 7)) << 4);
  const uint32_t ya = cb + (lane >> 4) * 1024 + (8 * w + (lane & 7)) * 32 + ((((lane >> 3) ^ (lane >> 2)) & 1) << 4);
  wg_sync(1 + wg);
#pragma unroll
  for (int p = 0; p < 2; p++) {
    if (p == 0) wg_wait<1>();
    else wg_wait<0>();
    pin<16>(V + 16 * p);
#pragma unroll
    for (int i = 0; i < 4; i++) {
      const int j = i & 1;
      const float* x = V + 16 * p + 4 * j + (i & 2);
      e[p][i] = pack2(x[8], x[9]);
      e[2 + p][i] = pack2(x[0], x[1]);
      rot(e[p][i], e[2 + p][i], k.ta[1][j], k.tb[1][j]);
    }
    stsm4(za ^ (64 * p), e[p]);
    stsm4((za ^ (64 * p)) + 4096, e[2 + p]);
  }
  fence_async_smem();
  wg_sync(1 + wg);
  wg_fence();
  WgRS<64>::set<HI_SW128>(H, k.fi[0], dz);
#pragma unroll
  for (int ks = 1; ks < 4; ks++) WgRS<64>::mma<HI_SW128>(H, k.fi[ks], dz + 128 * ks);
  wg_commit();
  wg_wait<0>();
  pin<32>(H);
  if (lane == 0) mbar_arrive(bars + 8 * B_CVD);
  TSIF(w == 0, 88 + c);
#pragma unroll
  for (int j = 0; j < 8; j++)
    a[j >> 2][j & 3] = j < 2 ? pack2(H[4 * j], H[4 * j + 1]) : pack2(H[4 * j] + H[4 * j - 6], H[4 * j + 1] + H[4 * j - 5]);
  stsm4(ya, a[0]);
  stsm4(ya + 2048, a[1]);
  fence_async_smem();
  __syncwarp();
}

__device__ __forceinline__ void prep_slab(uint4* res, const uint2* sw, uint32_t sb, int slab, int w, int lane) {
  const int t = lane & 3, tp = (lane & 7) >> 1, pos = 8 * tp + 2 * (((lane >> 3) + tp) & 3) + (lane & 1);
  const uint32_t base = sb + OFF_KVS + slab * KVS_BYTES + pos * 128;
  uint32_t kk[2][4][4], vv[2][4];
  mbar_wait(sb + OFF_BAR + 8 * (B_KV + slab), 0);
#pragma unroll
  for (int h = 0; h < 2; h++) {
#pragma unroll
    for (int j = 0; j < 4; j++) {
      const uint32_t a = base + 128 * j;
      ldsm4t(kk[h][j], a + (((w + 4 * h) ^ ((a >> 7) & 7)) << 4));
    }
    const uint32_t a = base + KVS_V;
    ldsm4t(vv[h], a + (((w + 4 * h) ^ ((a >> 7) & 7)) << 4));
  }
#pragma unroll
  for (int h = 0; h < 2; h++) {
    uint32_t (&k)[4][4] = kk[h];
    uint32_t (&v)[4] = vv[h];
    const uint32_t w0 = __byte_perm(sw[h].x, 0, 0x1010), w1 = __byte_perm(sw[h].x, 0, 0x3232);
    const uint32_t w2 = __byte_perm(sw[h].y, 0, 0x1010), w3 = __byte_perm(sw[h].y, 0, 0x3232);
#pragma unroll
    for (int m = 0; m < 4; m++)
      v[m] = bmul(badd(badd(badd(bmul(k[0][m], w3), bmul(k[1][m], w2)), bmul(k[2][m], w1)), bmul(k[3][m], w0)), v[m]);
    uint32_t a[4];
#pragma unroll
    for (int m = 0; m < 4; m++) a[m] = (t & 1) ? v[(m + 3) & 3] : v[m];
    res[h] = (t & 2) ? make_uint4(a[2], a[3], a[0], a[1]) : make_uint4(a[0], a[1], a[2], a[3]);
  }
}

__device__ __forceinline__ void prep_gate(const Params& p, uint32_t sb, int b, int w, int lane) {
  uint2 gw[5], x[4][5];
#pragma unroll
  for (int j = 0; j < 5; j++) gw[j] = ldg64(reinterpret_cast<const uint2*>(p.gate_w) + lane + 32 * j);
#pragma unroll
  for (int i = 0; i < 4; i++)
#pragma unroll
    for (int j = 0; j < 5; j++)
      x[i][j] = ldg64(reinterpret_cast<const uint2*>(p.q) + (16 * b + 4 * w + i) * (DIM / 4) + lane + 32 * j);
  float s[4];
#pragma unroll
  for (int i = 0; i < 4; i++) {
    s[i] = 0.f;
#pragma unroll
    for (int j = 0; j < 5; j++) {
      const uint32_t m0 = bmul(x[i][j].x, gw[j].x), m1 = bmul(x[i][j].y, gw[j].y);
      s[i] += (bf_lo(m0) + bf_hi(m0)) + (bf_lo(m1) + bf_hi(m1));
    }
  }
  const bool h = lane & 16, q = lane & 8;
  const float a = (h ? s[2] : s[0]) + __shfl_xor_sync(0xffffffffu, h ? s[0] : s[2], 16);
  const float c = (h ? s[3] : s[1]) + __shfl_xor_sync(0xffffffffu, h ? s[1] : s[3], 16);
  float z = (q ? c : a) + __shfl_xor_sync(0xffffffffu, q ? a : c, 8);
#pragma unroll
  for (int o = 4; o > 0; o >>= 1) z += __shfl_xor_sync(0xffffffffu, z, o);
  z = bf_lo(pack2(z, 0.f));
  z = bf_lo(pack2(__fdividef(1.f, 1.f + __expf(-z)), 0.f));
  mbar_wait(sb + OFF_BAR + 8 * B_S3, 0);
  if ((lane & 7) == 0) asm volatile("st.shared.f32 [%0], %1;" ::"r"(sb + OFF_GATE + 64 * (b & 7) + 16 * w + (lane >> 1)), "f"(z) : "memory");
  fence_async_smem();
}

__device__ __forceinline__ uint32_t bmax(uint32_t a, uint32_t b) {
  uint32_t d;
  asm("max.bf16x2 %0, %1, %2;" : "=r"(d) : "r"(a), "r"(b));
  return d;
}
__device__ __forceinline__ void softmax_two(const float (&l)[2][2], uint32_t& p0, uint32_t& p1) {
  constexpr float kScale = 0.22360679774997896f, kLog2e = 1.4426950408889634f;
  const uint32_t r0 = pack2(l[0][0], l[1][0]), r1 = pack2(l[0][1], l[1][1]);
  const uint32_t x0 = pack2(bf_lo(r0) * kScale, bf_hi(r0) * kScale), x1 = pack2(bf_lo(r1) * kScale, bf_hi(r1) * kScale);
  uint32_t m = bmax(x0, x1);
  m = bmax(m, __shfl_xor_sync(0xffffffffu, m, 1));
  m = bmax(m, __shfl_xor_sync(0xffffffffu, m, 2));
  const float m0 = bf_lo(m) * kLog2e, m1 = bf_hi(m) * kLog2e;
  p0 = pack2(ex2(bf_lo(x0) * kLog2e - m0), ex2(bf_lo(x1) * kLog2e - m0));
  p1 = pack2(ex2(bf_hi(x0) * kLog2e - m1), ex2(bf_hi(x1) * kLog2e - m1));
}

__device__ __forceinline__ void halo_read(uint32_t (&kpv)[10], uint32_t (&vpv)[10], uint32_t (&tg)[7], const uint4* hp) {
#pragma unroll
  for (int j = 0; j < 7; j++) {
    uint32_t x0, x1, x2;
    asm volatile("ld.relaxed.gpu.global.v4.u32 {%0, %1, %2, %3}, [%4];"
                 : "=r"(x0), "=r"(x1), "=r"(x2), "=r"(tg[j]) : "l"(hp + 32 * j) : "memory");
    if (j < 4) kpv[3 * j] = x0; else vpv[3 * j - 10] = x0;
    if (j < 3) kpv[3 * j + 1] = x1; else vpv[3 * j - 9] = x1;
    if (j < 3) kpv[3 * j + 2] = x2; else if (j < 6) vpv[3 * j - 8] = x2;
  }
}

template <int ROT>
__device__ __forceinline__ void pack_qkv(const float* acc, uint32_t (&qlo)[10], uint32_t (&qhi)[10], uint32_t (&klo)[10],
                                         uint32_t (&khi)[10], uint32_t (&vlo)[10], uint32_t (&vhi)[10]) {
#pragma unroll
  for (int j = 0; j < 10; j++) {
    const int x = (j + ROT) % 10, tq = x < 8 ? x : 16 + x, tk = x < 8 ? 8 + x : 18 + x, tv = x < 8 ? 16 + x : 20 + x;
    khi[j] = pack2(acc[4 * tk + 2], acc[4 * tk + 3]);
    vhi[j] = movm(pack2(acc[4 * tv + 2], acc[4 * tv + 3]));
    qlo[j] = pack2(acc[4 * tq], acc[4 * tq + 1]);
    qhi[j] = pack2(acc[4 * tq + 2], acc[4 * tq + 3]);
    klo[j] = pack2(acc[4 * tk], acc[4 * tk + 1]);
    vlo[j] = pack2(acc[4 * tv], acc[4 * tv + 1]);
    asm volatile("" : "+r"(khi[j]), "+r"(qlo[j]), "+r"(qhi[j]), "+r"(klo[j]), "+r"(vlo[j]));
  }
}

template <int ROT> __device__ __forceinline__ void halo_send(const float* acc, uint4* ho, uint32_t tag) {
#pragma unroll
  for (int j = 0; j < 7; j++) {
    uint32_t x[3];
#pragma unroll
    for (int e = 0; e < 3; e++) {
      const int i = 3 * j + e, y = (i % 10 + ROT) % 10, tk = y < 8 ? 8 + y : 18 + y, tv = y < 8 ? 16 + y : 20 + y;
      x[e] = i < 10 ? pack2(acc[4 * tk + 2], acc[4 * tk + 3]) : i < 20 ? movm(pack2(acc[4 * tv + 2], acc[4 * tv + 3])) : 0u;
    }
    asm volatile("st.relaxed.gpu.global.v4.u32 [%0], {%1, %2, %3, %4};" ::"l"(ho + 32 * j), "r"(x[0]), "r"(x[1]), "r"(x[2]), "r"(tag) : "memory");
  }
}

__device__ __forceinline__ void attention(float* acc, uint32_t sb, int b, int par, int w, int lane, uint32_t tag, FftConst& fc) {
  const int g = lane >> 2, t = lane & 3;
  uint32_t klo[10], khi[10], vlo[10], vhi[10], qlo[10], qhi[10], kpv[10], vpv[10];
  if (w == 3 && b < NCTA - 8) {
    uint4* ho = g_halo + (b * 2 + par) * 224 + lane;
    if (tail_first(b & 7)) halo_send<8>(acc, ho, tag);
    else halo_send<0>(acc, ho, tag);
    TSIF(par == 0, 76);
    pin<120>(acc);
  }
  if (tail_first(b & 7)) pack_qkv<8>(acc, qlo, qhi, klo, khi, vlo, vhi);
  else pack_qkv<0>(acc, qlo, qhi, klo, khi, vlo, vhi);
  const uint32_t xa = sb + OFF_KVX + (par * 3) * 2560 + lane * 16;
  if (w < 3) {
    sts128(xa + w * 2560, khi[0], khi[1], khi[2], khi[3]);
    sts128(xa + w * 2560 + 512, khi[4], khi[5], khi[6], khi[7]);
    sts128(xa + w * 2560 + 1024, khi[8], khi[9], vhi[0], vhi[1]);
    sts128(xa + w * 2560 + 1536, vhi[2], vhi[3], vhi[4], vhi[5]);
    sts128(xa + w * 2560 + 2048, vhi[6], vhi[7], vhi[8], vhi[9]);
  }
  TSIF(par == 0 && w == 1, 64);
#pragma unroll
  for (int j = 0; j < 10; j++) vlo[j] = movm(vlo[j]);
  const bool far0 = 2 * t > g, far1 = 2 * t + 1 > g;
  const uint32_t mfar = (far0 ? 0x0000FFFFu : 0u) | (far1 ? 0xFFFF0000u : 0u);
  float slo[4][2], lg[2][2];
  uint32_t phi[4], plo[4], qml[4], qmh[4];
#pragma unroll
  for (int h = 0; h < 4; h++) {
    const int f = h == 0 ? 0 : h == 1 ? 3 : h == 2 ? 5 : 8, hf = h < 2 ? 2 : 7;
    const bool mine = (h & 1) ? t >= 2 : t < 2;
    qml[h] = mine ? qlo[hf] : 0u;
    qmh[h] = mine ? qhi[hf] : 0u;
    float a[4] = {0.f, 0.f, 0.f, 0.f}, c[4] = {0.f, 0.f, 0.f, 0.f};
    mma16816(a, qlo[f], qhi[f], qlo[f + 1], qhi[f + 1], klo[f], klo[f + 1]);
    mma16816(c, qlo[f], qhi[f], qlo[f + 1], qhi[f + 1], khi[f], khi[f + 1]);
    mma1688(a, qml[h], qmh[h], klo[hf]);
    mma1688(c, qml[h], qmh[h], khi[hf]);
    slo[h][0] = a[0];
    slo[h][1] = a[1];
    lg[h & 1][0] = far0 ? a[2] : c[2];
    lg[h & 1][1] = far1 ? a[3] : c[3];
    if (h & 1) softmax_two(lg, phi[h - 1], phi[h]);
  }
  TSIF(par == 0 && w == 1, 65);
  wg_sync(1 + par);
  TSIF(par == 0 && w == 1, 66);
  const bool nohist = (w == 0) && (b < 8);
  const uint4* hp = g_halo + ((b - 8) * 2 + par) * 224 + lane;
  uint32_t tg[7];
  if (w > 0) {
    const uint4 v0 = lds128(xa + (w - 1) * 2560), v1 = lds128(xa + (w - 1) * 2560 + 512), v2 = lds128(xa + (w - 1) * 2560 + 1024);
    const uint4 v3 = lds128(xa + (w - 1) * 2560 + 1536), v4 = lds128(xa + (w - 1) * 2560 + 2048);
    kpv[0] = v0.x; kpv[1] = v0.y; kpv[2] = v0.z; kpv[3] = v0.w; kpv[4] = v1.x; kpv[5] = v1.y; kpv[6] = v1.z; kpv[7] = v1.w;
    kpv[8] = v2.x; kpv[9] = v2.y; vpv[0] = v2.z; vpv[1] = v2.w; vpv[2] = v3.x; vpv[3] = v3.y; vpv[4] = v3.z; vpv[5] = v3.w;
    vpv[6] = v4.x; vpv[7] = v4.y; vpv[8] = v4.z; vpv[9] = v4.w;
  } else if (nohist) {
#pragma unroll
    for (int j = 0; j < 10; j++) kpv[j] = vpv[j] = 0u;
  } else {
    TSIF(par == 0, 77);
    halo_read(kpv, vpv, tg, hp);
  }
  if (w == 0 && !nohist) {
    int spins = 0;
    while (true) {
      bool ok = true;
#pragma unroll
      for (int j = 0; j < 7; j++) ok = ok && tg[j] == tag;
      if (__all_sync(0xffffffffu, ok) || ++spins > SPIN_LIMIT) break;
      halo_read(kpv, vpv, tg, hp);
    }
    TSIF(par == 0, 79);
  }
#pragma unroll
  for (int h = 0; h < 4; h++) {
    const int f = h == 0 ? 0 : h == 1 ? 3 : h == 2 ? 5 : 8, hf = h < 2 ? 2 : 7;
    float a[4] = {0.f, 0.f, 0.f, 0.f};
    mma16816(a, qlo[f], qhi[f], qlo[f + 1], qhi[f + 1], kpv[f], kpv[f + 1]);
    mma1688(a, qml[h], qmh[h], kpv[hf]);
    const float ninf = __int_as_float(0xff800000);
    lg[h & 1][0] = far0 ? (nohist ? ninf : a[0]) : slo[h][0];
    lg[h & 1][1] = far1 ? (nohist ? ninf : a[1]) : slo[h][1];
    if (h & 1) softmax_two(lg, plo[h - 1], plo[h]);
  }
  TSIF(par == 0 && w <= 1, 67 + w);
  mbar_wait(sb + OFF_BAR + 8 * B_HA, 0);
  fft_matrices(fc, sb, w, lane);
  uint32_t ov[20];
#pragma unroll
  for (int hp = 0; hp < 2; hp++) {
    const int hf = hp ? 7 : 2;
    float sh[4] = {0.f, 0.f, 0.f, 0.f}, i0 = 0.f, i1 = 0.f;
#pragma unroll
    for (int e = 0; e < 2; e++) {
      const int h = 2 * hp + e, f = h == 0 ? 0 : h == 1 ? 3 : h == 2 ? 5 : 8;
      const uint32_t a0 = plo[h] & mfar, a2 = plo[h] & ~mfar, a3 = phi[h] & mfar, c1 = phi[h] & ~mfar;
      float sum[4] = {0.f, 0.f, 0.f, 0.f};
      mma1688(sum, plo[h], phi[h], 0x3F803F80u);
      const float r0 = rcp(sum[0]), r1 = rcp(sum[2]);
#pragma unroll
      for (int j = f; j < f + 2; j++) {
        float o[4] = {0.f, 0.f, 0.f, 0.f};
        mma16816(o, a0, 0u, a2, a3, vpv[j], vlo[j]);
        mma1688(o, 0u, c1, vhi[j]);
        ov[2 * j] = pack2(o[0] * r0, o[1] * r0);
        ov[2 * j + 1] = pack2(o[2] * r1, o[3] * r1);
      }
      const bool mine = e ? g >= 4 : g < 4;
      mma16816(sh, a0, 0u, a2, a3, mine ? vpv[hf] : 0u, mine ? vlo[hf] : 0u);
      mma1688(sh, 0u, c1, mine ? vhi[hf] : 0u);
      if (e == 0 || t >= 2) {
        i0 = r0;
        i1 = r1;
      }
    }
    ov[2 * hf] = pack2(sh[0] * i0, sh[1] * i0);
    ov[2 * hf + 1] = pack2(sh[2] * i1, sh[3] * i1);
  }
  TS(32 + 4 * par + w);
  mbar_wait(sb + OFF_BAR + 8 * B_P1, 0);
  const uint32_t oa = sb + OFF_OA + (lane >> 4) * 2048 + (32 * w + 2 * (lane & 15) + par) * 16;
#pragma unroll
  for (int j = 0; j < 5; j++) stsm4(oa + 4096 * j, ov + 4 * j);
  TSIF(par == 0 && w == 0, 120);
  fence_async_smem();
  TSIF(par == 0 && w == 0, 121);
  __syncwarp();
  if (lane == 0) mbar_arrive(sb + OFF_BAR + 8 * B_ATTN);
  TSM(w == 0 || w == 2, 122 + par + (w == 2 ? 3 : 0));
}

struct Maps {
  CUtensorMap x, wm, wt, k, v, y, wo, qm, qt, om, ot, yl, ol, wh;
};

__device__ __forceinline__ void load_stage(uint32_t sb, int kb, int b, const Maps& m) {
  const uint32_t st = sb + (kb & 3) * STAGE_BYTES, bar = sb + OFF_BAR + 8 * (B_FULL1 + (kb & 3));
  const int r = b >> 3, hg = b & 7, slab = kb - KV_KB;
  const bool kv = slab >= 0 && slab < 5;
  const uint32_t kbar = sb + OFF_BAR + 8 * (B_KV + slab), dst = sb + OFF_KVS + slab * KVS_BYTES;
  mbar_expect_tx(bar, STAGE_BYTES);
  if (kv) mbar_expect_tx(kbar, KVS_BYTES);
  tma_3d(st, &m.x, 64 * kb, 64 * r, 0, bar);
  tma_3d(st + ST_W, &m.wm, 80 * hg + (tail_first(hg) ? 16 : 0), 64 * kb, 0, bar);
  tma_3d(st + ST_WT, &m.wt, 80 * hg + (tail_first(hg) ? 0 : 64), 64 * kb, 0, bar);
  if (kv) tma_3d(dst, &m.k, 0, 32 * (b >> 1) - 3, 2 * slab + (b & 1), kbar);
  if (kv) tma_3d(dst + KVS_V, &m.v, 0, 32 * (b >> 1), 2 * slab + (b & 1), kbar);
}

__global__ void __launch_bounds__(NTHR, 1) fused_kernel(const __grid_constant__ Maps m, const Params p) {
  extern __shared__ __align__(1024) uint8_t smem[];
  const uint32_t sb = (uint32_t)__cvta_generic_to_shared(smem);
  const uint32_t bars = sb + OFF_BAR;
  const int tid = threadIdx.x, lane = tid & 31;
  int b = blockIdx.x;
  b = (((b & 63) >> 3) * 2 + (b & 1)) * 8 + (((b < 64 ? 0x6521 : 0x7430) >> (4 * ((b >> 1) & 3))) & 7);
  const int r = b >> 3, hg = b & 7;

  if (tid == T_ISSUE) {
    TSM(true, 0);
#pragma unroll
    for (int i = 0; i < 4; i++) mbar_init(bars + 8 * (B_F0 + i), 1);
    fence_async_smem();
#pragma unroll
    for (int i = 0; i < 4; i++) {
      mbar_expect_tx(bars + 8 * (B_F0 + i), (i ? 0 : ST_W) + 6144);
      if (i == 0) tma_3d(sb, &m.x, 0, 64 * r, 0, bars + 8 * B_F0);
      tma_3d(sb + ST_W + 6144 * i, &m.wh, 80 * hg + (tail_first(hg) ? 16 : 0), 16 * i, 0, bars + 8 * (B_F0 + i));
    }
#pragma unroll
    for (int i = 0; i < 4; i++) mbar_init(bars + 8 * (B_FULL1 + i), 1);
    fence_async_smem();
    mbar_expect_tx(bars + 8 * B_FULL1, STAGE_BYTES - ST_WT);
    tma_3d(sb + ST_WT, &m.wt, 80 * hg + (tail_first(hg) ? 0 : 64), 0, 0, bars + 8 * B_FULL1);
    load_stage(sb, 1, b, m);
  } else if (tid == T_INIT) {
#pragma unroll
    for (int i = 0; i < B_F0; i++) mbar_init(bars + 8 * i, i < B_GATE ? 8 : i < B_CVD ? 4 : i == B_CVD ? 20 : 1);
    fence_async_smem();
  }
  const int warp = __shfl_sync(0xffffffffu, tid >> 5, 0), wg = warp >> 2, w = warp & 3;
  __syncthreads();

  if (wg == 3) {
    asm volatile("setmaxnreg.dec.sync.aligned.u32 56;");
    if (w == 0) {
      if (lane == 0) {
#pragma unroll 1
        for (int kb = 2; kb < 10; kb++) {
          if (kb >= 4) mbar_wait(bars + 8 * (kb == 7 ? B_E3 : B_EMPTY1 + (kb & 3)), (kb >> 3) & 1);
          TSIF(kb >= 4, 44 + kb);
          load_stage(sb, kb, b, m);
          TSIF(kb == 3, 60);
          if (kb == 9) mbar_arrive(bars + 8 * B_LAST);
        }
        mbar_wait(bars + 8 * B_WOP, 0);
        mbar_wait(bars + 8 * B_EPOCH, 0);
        flag_wait(g_cnt + C_W + 32 * hg, (lds32(sb + OFF_EPOCH) + 1) * 16);
        TS(30);
#pragma unroll 1
        for (int j = 0; j < 8; j++) {
          if (j >= 6) mbar_wait(bars + 8 * (B_EMPTY2 + j - 6), 0);
          if (j == 4) mbar_wait(bars + 8 * B_ORB, 0);
          TSIF(j >= 6, 100 + j);
          mbar_expect_tx(bars + 8 * (B_FULL2 + j), j == 0 ? WO_BYTES : j == 5 ? O_BYTES + WO_BYTES + 512 : O_BYTES + WO_BYTES);
          bulk_load(sb + off_w(j), g_WO + (hg * 8 + step_src(hg, j)) * 800, WO_BYTES, bars + 8 * (B_FULL2 + j));
        }
        mbar_wait(bars + 8 * (B_EMPTY2 + 3), 0);
        mbar_expect_tx(bars + 8 * B_QF, O_BYTES);
        tma_2d(sb + OFF_QS, &m.qm, 80 * hg, 128 * r, bars + 8 * B_QF);
        tma_2d(sb + OFF_QT, &m.qt, 80 * hg + 64, 128 * r, bars + 8 * B_QF);
      }
    } else if (w == 1) {
      unsigned epoch = 0;
      if (lane == 0) {
        epoch = atomicAdd(g_cnt + C_LAUNCH, 1u) / NCTA;
        asm volatile("st.shared.u32 [%0], %1;" ::"r"(sb + OFF_EPOCH), "r"(epoch) : "memory");
        mbar_arrive(bars + 8 * B_EPOCH);
        mbar_wait(bars + 8 * B_KVD, 0);
        mbar_expect_tx(bars + 8 * B_HB, 5 * 4096);
#pragma unroll 1
        for (int c = 0; c < 5; c++) {
          if (c == 3) mbar_wait(bars + 8 * B_S3, 0);
          bulk_load(sb + off_ch(c) + U_BYTES, p.ssm_k + (5 * b + c) * SEQ, 4096, bars + 8 * B_HB);
        }
#pragma unroll
        for (int c = 0; c < 4; c++) mbar_expect_tx(bars + 8 * (B_U + c), c < 3 ? U_BYTES : 2 * U_BYTES);
        const uint4* usrc = g_U + 5 * b * U_PITCH;
        mbar_wait(bars + 8 * B_USIG, 0);
        flag_wait(g_cnt + C_PREP + 32 * (b & 15), (epoch + 1) * NCTA);
        TS(23);
#pragma unroll
        for (int c = 0; c < 5; c++) {
          if (c == 3) mbar_wait(bars + 8 * (B_U + 2), 0);
          bulk_load(sb + off_ch(c), usrc + c * U_PITCH, U_BYTES, bars + 8 * (B_U + (c < 3 ? c : 3)));
          TSIF(c == 0 || c == 4, 116 + (c >> 2));
        }
      }
      epoch = __shfl_sync(0xffffffffu, epoch, 0);
      if (lane < 8) {
        const int src = (b & ~7) | step_src(hg, lane);
        mbar_wait(bars + 8 * B_ATTN, 0);
        TS(20);
        bool seen = false;
#pragma unroll 1
        for (int spins = 0; spins < SPIN_LIMIT; spins++) {
          const bool now = !seen && (int)(flag_read(g_cnt + C_O + 32 * src) - (epoch + 1)) >= 0;
          if (now && lane >= 1 && lane < 4) bulk_load(sb + off_o(lane), g_O + src * 1280, O_BYTES, bars + 8 * (B_FULL2 + lane));
          seen = seen || now;
          if (__all_sync(0xff, seen)) break;
        }
        TS(21);
        if (lane == 5) bulk_load(sb + OFF_GATE, g_gate + 128 * r, 512, bars + 8 * (B_FULL2 + 5));
#pragma unroll 1
        for (int j = 4; j < 8; j++) {
          if (lane == j) {
            mbar_wait(bars + 8 * (j < 6 ? B_C34 : B_EMPTY2 + j - 6), 0);
            bulk_load(sb + off_o(j), g_O + src * 1280, O_BYTES, bars + 8 * (B_FULL2 + j));
          }
          __syncwarp(0xff);
        }
        TS(22);
      }
    } else if (w == 2) {
      mbar_wait(bars + 8 * B_PREP, 0);
      flag_signal(g_cnt + C_PREP, 16, lane);
      TS(25);
      if (lane == 0) {
        mbar_arrive(bars + 8 * B_USIG);
        mbar_expect_tx(bars + 8 * B_ORB, O_BYTES / 4 + 64);
        mbar_wait(bars + 8 * B_GATE, 0);
        publish(g_gate + 16 * b, sb + OFF_GATE + 64 * hg, 64);
        bulk_load(sb + OFF_GATE + 64 * hg, g_gate + 16 * b, 64, bars + 8 * B_ORB);
        mbar_wait(bars + 8 * B_ATTN, 0);
        publish(g_O + b * 1280, sb + OFF_OA, O_BYTES);
        tma_2d(sb + OFF_KVX + 10240, &m.ol, 48, b * 160, bars + 8 * B_ORB);
        TS(74);
        mbar_wait(bars + 8 * B_ORB, 0);
        flag_bump(g_cnt + C_O + 32 * b);
        TS(26);
      }
    } else {
      if (lane == 0) {
        uint4* dst = g_WO + (hg * 8 + (r >> 1)) * 800 + (r & 1) * 80;
        mbar_wait(bars + 8 * B_S3, 0);
        asm volatile("cp.async.bulk.prefetch.L2.global [%0], 6400;" ::"l"(p.wo + b * 3200) : "memory");
        mbar_wait(bars + 8 * B_P1, 0);
        mbar_wait(bars + 8 * WB_TRIG, 0);
        mbar_expect_tx(bars + 8 * B_WST, WO_BYTES / 2);
        tma_3d(sb + OFF_WA, &m.wo, 0, 40 * r, 5 * hg, bars + 8 * B_WST);
        mbar_wait(bars + 8 * B_WST, 0);
#pragma unroll 1
        for (int n = 0; n < 5; n++) bulk_store(dst + 160 * n, sb + OFF_WA + 1280 * n, 1280);
        bulk_wait_read();
        mbar_expect_tx(bars + 8 * B_WST, WO_BYTES / 2);
#pragma unroll 1
        for (int n = 0; n < 5; n++) bulk_load(sb + OFF_WA + 1280 * n, dst + 160 * n, 1280, bars + 8 * B_WST);
        mbar_wait(bars + 8 * B_WST, 1);
        flag_bump(g_cnt + C_W + 32 * hg);
        mbar_arrive(bars + 8 * B_WOP);
        TS(71);
        mbar_expect_tx(bars + 8 * B_C34, 3 * (U_BYTES / 4));
        mbar_expect_tx(bars + 8 * B_YRB, 2 * (U_BYTES / 4));
#pragma unroll 1
        for (int c = 0; c < 5; c++) {
          mbar_wait(bars + 8 * (B_YST + c), 0);
          publish(g_U + (5 * b + c) * U_PITCH, sb + off_ch(c), U_BYTES);
          tma_2d(sb + off_ch(c), &m.yl, 48, (5 * b + c) * (U_PITCH / 8), bars + 8 * (c < 3 ? B_C34 : B_YRB));
        }
        TS(75);
        mbar_wait(bars + 8 * B_C34, 0);
        mbar_wait(bars + 8 * B_YRB, 0);
        flag_bump(g_cnt + C_Y + 32 * (b >> 4));
        TS(27);
        mbar_expect_tx(bars + 8 * B_YFULL, 20480);
        flag_wait(g_cnt + C_Y + 32 * hg, (lds32(sb + OFF_EPOCH) + 1) * 16);
        TS(24);
        tma_2d(sb + OFF_YT, &m.y, 128 * r, 80 * hg, bars + 8 * B_YFULL);
        tma_2d(sb + OFF_YT + 10240, &m.y, 128 * r + 64, 80 * hg, bars + 8 * B_YFULL);
      }
    }
  } else {
    asm volatile("setmaxnreg.inc.sync.aligned.u32 152;");
    FftConst fc;
    if (wg < 2) {
      float acc[120];
#pragma unroll
      for (int i = 0; i < 120; i++) acc[i] = 0.f;
      const uint32_t da = desc_lo(sb + wg * 8192, 16), db = desc_lo(sb + ST_W, 8192), dc = desc_lo(sb + ST_WT, 2048);
#pragma unroll
      for (int k = 0; k < 4; k++) {
        mbar_wait(bars + 8 * (B_F0 + k), 0);
        TSIF(w == 0 && wg == 0 && k == 0, 1);
        wg_fence();
        WgSST<192>::mma<HI_SW128, HI_SW128>(acc, da + 2 * k, desc_lo(sb + ST_W, 2048) + 384 * k, 1);
        wg_commit();
      }
      mbar_wait(bars + 8 * B_FULL1, 0);
      wg_fence();
#pragma unroll
      for (int k = 0; k < 4; k++) WgSST<48>::mma<HI_SW128, HI_SW32>(acc + 96, da + 2 * k, dc + 32 * k, 1);
      wg_commit();
#pragma unroll 1
      for (int kb = 1; kb < 10; kb++) {
        mbar_wait(bars + 8 * (B_FULL1 + (kb & 3)), (kb >> 2) & 1);
        const uint32_t so = (kb & 3) * (STAGE_BYTES >> 4);
        wg_fence();
#pragma unroll
        for (int k = 0; k < 4; k++) {
          WgSST<192>::mma<HI_SW128, HI_SW128>(acc, da + so + 2 * k, db + so + 128 * k, 1);
          WgSST<48>::mma<HI_SW128, HI_SW32>(acc + 96, da + so + 2 * k, dc + so + 32 * k, 1);
        }
        wg_commit();
        wg_wait<1>();
        if (lane == 0) mbar_arrive(bars + 8 * (kb == 4 ? B_E3 : B_EMPTY1 + ((kb - 1) & 3)));
      }
      mbar_wait(bars + 8 * B_EPOCH, 0);
      const uint32_t tag = lds32(sb + OFF_EPOCH) + 1;
      mbar_wait(bars + 8 * B_S3, 0);
      wg_wait<0>();
      pin<120>(acc);
      if (lane == 0) mbar_arrive(bars + 8 * B_P1);
      TSM(w == 0, 3 + wg);
      attention(acc, sb, b, wg, w, lane, tag, fc);
    } else {
      const int tw = tid & 127, chl = 64 * (b & 1) + 8 * w + (lane >> 2);
      uint4* up = g_U + chl * U_PITCH + ((4 * (b >> 1) + (lane & 3)) ^ ((b >> 2) & 1));
      uint2 sw[10];
      uint32_t dv = 0;
      if (lane < 5) dv = __ldg(reinterpret_cast<const unsigned short*>(p.ssm_D) + 5 * b + lane);
#pragma unroll
      for (int i = 0; i < 10; i++) sw[i] = ldg64(reinterpret_cast<const uint2*>(p.shift_k) + chl + 128 * (i >> 1) + 32 * (i & 1));
      uint32_t tab[12];
      uint32_t tt[2];
      fft_tables(tab, tw);
      fft_twiddles(tt, tw);
      uint4 res[10];
#pragma unroll
      for (int i = 0; i < 10; i++) res[i] = make_uint4(0, 0, 0, 0);
#pragma unroll 1
      for (int slab = 0; slab < 5; slab++) {
#pragma unroll
        for (int i = 0; i < 8; i++) res[i] = res[i + 2];
        prep_slab(res + 8, sw, sb, slab, w, lane);
        TSIF(w == 0, 99 + 4 * slab);
#pragma unroll
        for (int i = 0; i < 8; i++) sw[i] = sw[i + 2];
      }
      TSIF(w == 0, 28);
      __syncwarp();
      if (lane == 0) mbar_arrive(bars + 8 * B_KVD + ((res[8].x ^ res[9].x) & p.zero));
      mbar_wait(bars + 8 * B_KVD, 0);
      fft_tables_store(tab, sb, tw);
      mbar_wait(bars + 8 * B_LAST, 0);
#pragma unroll
      for (int i = 0; i < 10; i++) up[(128 * (i >> 1) + 32 * (i & 1)) * U_PITCH] = res[i];
      __syncwarp();
      if (lane == 0) mbar_arrive(bars + 8 * B_PREP);
      TSIF(w == 0, 5);
      mbar_wait(bars + 8 * B_LAST, 0);
      prep_gate(p, sb, b, w, lane);
      __syncwarp();
      if (lane == 0) mbar_arrive(bars + 8 * B_GATE);
      TSIF(w == 0, 72);
      mbar_wait(bars + 8 * B_HB, 0);
      TSIF(w == 0, 2);
      const uint32_t ha = sb + U_BYTES + ((tw >> 3) * 16 + 8 + (tw & 7)) * 16;
      uint4 hv[5];
#pragma unroll
      for (int c = 0; c < 5; c++) hv[c] = lds128(ha + off_ch(c));
      __syncwarp();
#pragma unroll
      for (int c = 0; c < 5; c++) sts128((ha ^ 16) + off_ch(c), hv[c].x, hv[c].y, hv[c].z, hv[c].w);
      asm volatile("st.shared.v2.u32 [%0], {%1, %2};" ::"r"(sb + OFF_TT + 8 * tw), "r"(tt[0]), "r"(tt[1]) : "memory");
      if (tw < 5) asm volatile("st.shared.f32 [%0], %1;" ::"r"(sb + OFF_D + 4 * tw), "f"(bf_lo(dv) * 0.125f) : "memory");
      fence_async_smem();
      __syncwarp();
      if (lane == 0) mbar_arrive(bars + 8 * B_HA);
      TSIF(w == 0, 6);
      mbar_wait(bars + 8 * B_HA, 0);
      fft_matrices(fc, sb, w, lane);
    }

    TSM(w == 0 && wg == 2, 124);
#pragma unroll 1
    for (uint32_t tasks = wg == 0 ? TASK0 : wg == 1 ? TASK1 : TASK2; tasks; tasks >>= 4) {
      const int c = (tasks & 7) - 1;
      conv_channel(fc, sb, c, wg, w, lane);
      if (lane == 0) mbar_arrive(bars + 8 * (B_YST + c));
      TSM(w == 0, 10 + c);
    }

    if (wg != 1) {
      const int wg = warp >> 3;
      const int g = lane >> 2;
      float acc[40];
#pragma unroll
      for (int i = 0; i < 40; i++) acc[i] = 0.f;
      const uint32_t da = desc_lo(sb + wg * 1024, 2048), db = desc_lo(sb, 2560);
      mbar_wait(bars + 8 * B_ORB, 0);
      mbar_wait(bars + 8 * B_FULL2, 0);
      TSM(w == 0, 15 + wg);
#pragma unroll 1
      for (int j = 0; j < 8; j++) {
        if (j == 1 - wg) mbar_wait(bars + 8 * B_CVD, 0);
        mbar_wait(bars + 8 * (B_FULL2 + j), 0);
        TSM(w == 0 && wg == 0, 44 + (j < 4 ? j : j + 6));
        const uint32_t oa = da + (off_o(j) >> 4), ob = db + (off_w(j) >> 4);
        wg_fence();
#pragma unroll
        for (int k = 0; k < 5; k++) WgSST<80>::mma<HI_NONE, HI_SW32>(acc, oa + 256 * k, ob + 32 * k, 1);
        wg_commit();
        wg_wait<1>();
        if (j >= 1 && j <= 4 && lane == 0) mbar_arrive(bars + 8 * (B_EMPTY2 + j - 1));
      }
      TSIF(w == 0 && wg == 0, 113);
      const int tr = 64 * wg + 16 * w + (lane & 15);
      const uint32_t fm = sb + OFF_QS + tr * 128, fx = (lane >> 4) ^ (tr & 7);
      const uint32_t ft = sb + OFF_QT + tr * 32 + (((lane >> 4) ^ (tr >> 2)) & 1) * 16;
      const float g0 = __uint_as_float(lds32(sb + OFF_GATE + (64 * wg + 16 * w + g) * 4));
      const float g1 = __uint_as_float(lds32(sb + OFF_GATE + (64 * wg + 16 * w + 8 + g) * 4));
      const uint32_t ga = pack2(g0, g0), gb = pack2(g1, g1);
      const uint32_t na = pack2(1.f - g0, 1.f - g0), nb = pack2(1.f - g1, 1.f - g1);

      uint32_t qf[20];
      mbar_wait(bars + 8 * B_QF, 0);
      TSM(w == 0 && wg == 0, 99);
#pragma unroll
      for (int j = 0; j < 5; j++) ldsm4(qf + 4 * j, j < 4 ? fm + ((fx ^ (2 * j)) << 4) : ft);
#pragma unroll
      for (int i = 0; i < 20; i++) {
        qf[i] = bmul((i & 1) ? gb : ga, qf[i]);
        asm volatile("" : "+r"(qf[i]));
      }

      wg_wait<0>();
      pin<40>(acc);
      TSM(w == 0, 17 + wg);
      uint32_t pb[20];
#pragma unroll
      for (int j = 0; j < 10; j++) {
        pb[2 * j] = bmul(na, pack2(acc[4 * j], acc[4 * j + 1]));
        pb[2 * j + 1] = bmul(nb, pack2(acc[4 * j + 2], acc[4 * j + 3]));
        asm volatile("" : "+r"(pb[2 * j]), "+r"(pb[2 * j + 1]));
      }
      const uint32_t ya = sb + OFF_YT + wg * 10240 + ((lane >> 4) * 8 + (lane & 7)) * 128 +
                          (((2 * w + (((lane >> 3) & 1) ^ wg)) ^ (lane & 7)) << 4);
      mbar_wait(bars + 8 * B_YFULL, 0);
      TSM(w == 0 && wg == 0, 19);
#pragma unroll
      for (int j = 0; j < 5; j++) {
        uint32_t y[4];
        ldsm4t(y, ya + 2048 * j);
#pragma unroll
        for (int i = 0; i < 4; i++)
          qf[4 * j + i] = bfma(qf[4 * j + i], y[i], pb[4 * j + i]);
      }
#pragma unroll
      for (int j = 0; j < 5; j++) stsm4(j < 4 ? fm + ((fx ^ (2 * j)) << 4) : ft, qf + 4 * j);
      fence_async_smem();
      __syncwarp();
      if (lane == 0) {
        const int row = 64 * wg + 16 * w;
        asm volatile("cp.async.bulk.tensor.2d.global.shared::cta.bulk_group [%0, {%2, %3}], [%1];"
                     ::"l"(&m.om), "r"(sb + OFF_QS + row * 128), "r"(80 * hg), "r"(128 * r + row) : "memory");
        asm volatile("cp.async.bulk.tensor.2d.global.shared::cta.bulk_group [%0, {%2, %3}], [%1];"
                     ::"l"(&m.ot), "r"(sb + OFF_QT + row * 32), "r"(80 * hg + 64), "r"(128 * r + row) : "memory");
        asm volatile("cp.async.bulk.commit_group;\ncp.async.bulk.wait_group.read 0;" ::: "memory");
      }
      TSM(w == 0 || w == 3, 40 + 2 * wg + (w & 1));
    }
  }
}

typedef CUresult (*EncodeFn)(CUtensorMap*, CUtensorMapDataType, cuuint32_t, void*, const cuuint64_t*, const cuuint64_t*,
                             const cuuint32_t*, const cuuint32_t*, CUtensorMapInterleave, CUtensorMapSwizzle,
                             CUtensorMapL2promotion, CUtensorMapFloatOOBfill);

void encode(EncodeFn fn, CUtensorMap* tm, const void* base, int rank, const cuuint64_t* dims, const cuuint64_t* strides,
            const cuuint32_t* box, CUtensorMapSwizzle swz, int promo = 2) {
  const cuuint32_t ones[3] = {1, 1, 1};
  fn(tm, CU_TENSOR_MAP_DATA_TYPE_BFLOAT16, rank, const_cast<void*>(base), dims, strides, box, ones,
     CU_TENSOR_MAP_INTERLEAVE_NONE, swz, (CUtensorMapL2promotion)promo, CU_TENSOR_MAP_FLOAT_OOB_FILL_NONE);
}

}

extern "C" void kernel_launch(void* const* d_in, const int* in_sizes, int n_in, void* d_out, int out_size) {
  (void)in_sizes; (void)n_in; (void)out_size;
  Params p;
  p.q = (const __nv_bfloat16*)d_in[0];
  p.k = (const __nv_bfloat16*)d_in[1];
  p.v = (const __nv_bfloat16*)d_in[2];
  p.shift_k = (const __nv_bfloat16*)d_in[3];
  p.ssm_k = (const __nv_bfloat16*)d_in[4];
  p.ssm_D = (const __nv_bfloat16*)d_in[5];
  p.wqkv = (const __nv_bfloat16*)d_in[7];
  p.wo = (const __nv_bfloat16*)d_in[8];
  p.gate_w = (const __nv_bfloat16*)d_in[9];
  p.out = (__nv_bfloat16*)d_out;
  p.zero = 0;

  static EncodeFn fn = nullptr;
  static void *yaddr = nullptr, *oaddr = nullptr;
  if (!fn) {
    cudaDriverEntryPointQueryResult qr;
    void* f = nullptr;
    cudaGetDriverEntryPoint("cuTensorMapEncodeTiled", &f, cudaEnableDefault, &qr);
    fn = (EncodeFn)f;
    cudaGetSymbolAddress(&yaddr, g_U);
    cudaGetSymbolAddress(&oaddr, g_O);
    cudaFuncSetAttribute(fused_kernel, cudaFuncAttributeMaxDynamicSharedMemorySize, SMEM_BYTES);
  }
  Maps m;
  {
    const cuuint64_t dims[3] = {640, 1024, 2}, st[2] = {2560, 1280};
    const cuuint32_t box[3] = {64, 64, 2};
    encode(fn, &m.x, p.q, 3, dims, st, box, CU_TENSOR_MAP_SWIZZLE_128B, PR_X);
  }
  {
    const cuuint64_t dims[3] = {640, 640, 3}, st[2] = {3840, 1280};
    const cuuint32_t box[3] = {64, 64, 3}, boxt[3] = {16, 64, 3};
    encode(fn, &m.wm, p.wqkv, 3, dims, st, box, CU_TENSOR_MAP_SWIZZLE_128B, PR_W);
    encode(fn, &m.wt, p.wqkv, 3, dims, st, boxt, CU_TENSOR_MAP_SWIZZLE_32B, PR_T);
    const cuuint32_t boxh[3] = {64, 16, 3};
    encode(fn, &m.wh, p.wqkv, 3, dims, st, boxh, CU_TENSOR_MAP_SWIZZLE_128B, PR_W);
  }
  {
    const cuuint64_t dims[3] = {64, 2048, 10}, st[2] = {1280, 128};
    const cuuint32_t boxk[3] = {64, 35, 1}, boxv[3] = {64, 32, 1};
    encode(fn, &m.k, p.k, 3, dims, st, boxk, CU_TENSOR_MAP_SWIZZLE_128B, PR_K);
    encode(fn, &m.v, p.v, 3, dims, st, boxv, CU_TENSOR_MAP_SWIZZLE_128B, PR_K);
  }
  {
    const cuuint64_t dims[3] = {16, 640, 40}, st[2] = {1280, 32};
    const cuuint32_t box[3] = {16, 40, 5};
    encode(fn, &m.wo, p.wo, 3, dims, st, box, CU_TENSOR_MAP_SWIZZLE_32B, PR_O);
  }
  {
    const cuuint64_t dims[2] = {2048, 640}, st[1] = {U_PITCH * 16};
    const cuuint32_t box[2] = {64, 80};
    encode(fn, &m.y, yaddr, 2, dims, st, box, CU_TENSOR_MAP_SWIZZLE_128B);
    const cuuint64_t dl[2] = {64, DIM * U_PITCH / 8}, dol[2] = {64, NCTA * 160}, sl[1] = {128};
    const cuuint32_t bl[2] = {16, 32}, bol[2] = {16, 160};
    encode(fn, &m.yl, yaddr, 2, dl, sl, bl, CU_TENSOR_MAP_SWIZZLE_NONE, PR_R);
    encode(fn, &m.ol, oaddr, 2, dol, sl, bol, CU_TENSOR_MAP_SWIZZLE_NONE, PR_R);
  }
  {
    const cuuint64_t dims[2] = {640, 2048}, st[1] = {1280};
    const cuuint32_t bqm[2] = {64, 128}, bqt[2] = {16, 128}, bom[2] = {64, 16}, bot[2] = {16, 16};
    encode(fn, &m.qm, p.q, 2, dims, st, bqm, CU_TENSOR_MAP_SWIZZLE_128B, PR_O);
    encode(fn, &m.qt, p.q, 2, dims, st, bqt, CU_TENSOR_MAP_SWIZZLE_32B, PR_O);
    encode(fn, &m.om, p.out, 2, dims, st, bom, CU_TENSOR_MAP_SWIZZLE_128B, PR_S);
    encode(fn, &m.ot, p.out, 2, dims, st, bot, CU_TENSOR_MAP_SWIZZLE_32B, PR_S);
  }
  fused_kernel<<<NCTA, NTHR, SMEM_BYTES>>>(m, p);
}
```

```cpp
#include <cuda.h>
#include <cuda_bf16.h>
#include <cuda_runtime.h>
#include <stdint.h>

namespace {

constexpr int SEQ = 2048, DIM = 640, NCTA = 128, NTHR = 512;

#define KV_KB 2
#define DEV_EXIT 0
#define FENCE_LO 0
#define FENCE_HI 0
#define WB_TRIG B_USIG
#define T_ISSUE 288
#define G_IN 1
#define T_INIT 448
#define TASK0 0x3
#define TASK1 0x52
#define TASK2 0x41

constexpr uint32_t STAGE_BYTES = 47104, ST_W = 16384, ST_WT = 40960;
constexpr uint32_t O_BYTES = 20480, WO_BYTES = 12800;
constexpr uint32_t OFF_OA = 0;
constexpr uint32_t OFF_QS = 3 * O_BYTES, OFF_QT = OFF_QS + 16384;
constexpr uint32_t OFF_WC = 81920;
constexpr uint32_t OFF_WA = 94720;
constexpr uint32_t OFF_GATE = 145920;
constexpr uint32_t OFF_TT = 146432;
constexpr uint32_t OFF_KVX = 148480;
constexpr uint32_t OFF_CH3 = 163840;
constexpr uint32_t CH_BYTES = 12288, U_BYTES = 4096;
constexpr uint32_t OFF_FT = 225280, OFF_GT = 229376;
constexpr uint32_t OFF_CH0 = 188416;
constexpr uint32_t OFF_KVS = OFF_CH0, KVS_V = 4480, KVS_BYTES = 8576;
constexpr uint32_t OFF_YT = 163840;
constexpr uint32_t OFF_BAR = 231936;
constexpr uint32_t SMEM_BYTES = OFF_BAR + 512;

enum : uint32_t {
  B_EMPTY1 = 0, B_S3 = 3, B_E3 = 4, B_EMPTY2 = 5, B_ATTN = 9, B_P1 = 10,
  B_GATE = 11, B_HA = 12, B_KVD = 13, B_PREP = 14, B_YST = 15,
  B_CVD = 20,
  B_FULL2 = 21, B_U = 29, B_KV = 33, B_HB = 38, B_C34 = 39, B_YRB = 40, B_YFULL = 41, B_EPOCH = 42, B_LAST = 43,
  B_WOP = 44, B_USIG = 45, B_WST = 46, B_QF = 47, B_ORB = 48,
  B_F0 = 49, B_FULL1 = 53
};
constexpr uint32_t OFF_EPOCH = OFF_BAR + 8 * 58, OFF_D = OFF_BAR + 8 * 60;
__device__ __forceinline__ uint32_t off_o(int j) { return j < 4 ? OFF_OA + j * O_BYTES : j < 6 ? OFF_CH0 + (j - 4) * O_BYTES : OFF_OA + (j - 6) * O_BYTES; }
__device__ __forceinline__ uint32_t off_w(int j) { return j < 4 ? OFF_WA + j * WO_BYTES : j == 4 ? OFF_KVX : j == 5 ? OFF_WC : OFF_WA + (j - 6) * WO_BYTES; }
__device__ __forceinline__ int step_src(int hg, int j) { return j == 0 ? hg : j <= hg ? j - 1 : j; }
__device__ __forceinline__ bool tail_first(int hg) { return (hg & 3) == 3; }
__device__ __forceinline__ uint32_t off_ch(int c) { return (c < 3 ? OFF_CH0 : OFF_CH3 - 3 * CH_BYTES) + c * CH_BYTES; }

#define U_PITCH 264
__device__ __align__(1024) uint4 g_U[DIM * U_PITCH];
__device__ __align__(128) uint4 g_O[NCTA * 1280];
__device__ uint4 g_WO[64 * 800];
__device__ uint4 g_halo[NCTA * 2 * 7 * 32];
__device__ __align__(128) float g_gate[SEQ];
__device__ unsigned g_cnt[32 * (1 + 2 * 16 + 8 + NCTA)];
constexpr int C_LAUNCH = 0, C_PREP = 32, C_Y = 32 * 17, C_W = 32 * 33, C_O = 32 * 41;

#define TSM(cond, slot) do { } while (0)
#define TSIF(cond, slot) do { if (__LINE__ >= FENCE_LO && __LINE__ < FENCE_HI) sched_fence(); } while (0)
__device__ __forceinline__ void sched_fence() {
  asm volatile("{\n.reg .pred p;\n.reg .u32 c;\nmov.u32 c, %%clock;\nsetp.eq.u32 p, c, 0;\n@p st.shared.u32 [%0], c;\n}"
               ::"r"(1024 + OFF_EPOCH + 4) : "memory");
}
#define TS(slot) TSIF(true, slot)

struct Params {
  const __nv_bfloat16 *q, *k, *v, *shift_k, *ssm_k, *ssm_D, *wqkv, *wo, *gate_w;
  __nv_bfloat16* out;
  uint32_t zero;
};

constexpr int SPIN_LIMIT = 1 << 17;

__device__ __forceinline__ void mbar_init(uint32_t bar, uint32_t count) {
  asm volatile("mbarrier.init.shared::cta.b64 [%0], %1;" ::"r"(bar), "r"(count) : "memory");
}
__device__ __forceinline__ void mbar_expect_tx(uint32_t bar, uint32_t bytes) {
  asm volatile("mbarrier.arrive.expect_tx.shared::cta.b64 _, [%0], %1;" ::"r"(bar), "r"(bytes) : "memory");
}
__device__ __forceinline__ void mbar_arrive(uint32_t bar) {
  asm volatile("mbarrier.arrive.shared::cta.b64 _, [%0];" ::"r"(bar) : "memory");
}
__device__ __forceinline__ void mbar_wait(uint32_t bar, uint32_t parity) {
  uint32_t ok;
  int spins = 0;
  do {
      asm volatile("{\n.reg .pred p;\nmbarrier.try_wait.parity.shared::cta.b64 p, [%1], %2;\nselp.b32 %0, 1, 0, p;\n}"
                   : "=r"(ok) : "r"(bar), "r"(parity) : "memory");
    if (++spins > SPIN_LIMIT) break;
  } while (!ok);
}
__device__ __forceinline__ unsigned flag_read(const unsigned* p) {
  unsigned v;
  asm volatile("ld.relaxed.gpu.global.u32 %0, [%1];" : "=r"(v) : "l"(p) : "memory");
  return v;
}
__device__ __forceinline__ void flag_poll(const unsigned* p, unsigned target) {
  unsigned v;
  int spins = 0;
  do {
    asm volatile("ld.relaxed.gpu.global.u32 %0, [%1];" : "=r"(v) : "l"(p) : "memory");
    if (++spins > SPIN_LIMIT) break;
  } while ((int)(v - target) < 0);
}
__device__ __forceinline__ void flag_wait(const unsigned* p, unsigned target) {
  flag_poll(p, target);
}
__device__ __forceinline__ void flag_signal(unsigned* p, int n, int lane) {
  if (lane == 0) asm volatile("fence.release.gpu;" ::: "memory");
  __syncwarp();
  if (lane < n) asm volatile("red.relaxed.gpu.global.add.u32 [%0], 1;" ::"l"(p + 32 * lane) : "memory");
}
__device__ __forceinline__ void flag_bump(unsigned* p) {
  asm volatile("red.relaxed.gpu.global.add.u32 [%0], 1;" ::"l"(p) : "memory");
}
__device__ __forceinline__ void fence_async_smem() { asm volatile("fence.proxy.async.shared::cta;" ::: "memory"); }
__device__ __forceinline__ void wg_sync(int id) { asm volatile("bar.sync %0, 128;" ::"r"(id) : "memory"); }

__device__ __forceinline__ void tma_2d(uint32_t dst, const CUtensorMap* tm, int c0, int c1, uint32_t bar) {
  asm volatile("cp.async.bulk.tensor.2d.shared::cluster.global.mbarrier::complete_tx::bytes [%0], [%1, {%3, %4}], [%2];"
               ::"r"(dst), "l"(tm), "r"(bar), "r"(c0), "r"(c1) : "memory");
}
__device__ __forceinline__ void tma_3d(uint32_t dst, const CUtensorMap* tm, int c0, int c1, int c2, uint32_t bar) {
  asm volatile("cp.async.bulk.tensor.3d.shared::cluster.global.mbarrier::complete_tx::bytes [%0], [%1, {%3, %4, %5}], [%2];"
               ::"r"(dst), "l"(tm), "r"(bar), "r"(c0), "r"(c1), "r"(c2) : "memory");
}
__device__ __forceinline__ void bulk_load(uint32_t dst, const void* src, uint32_t bytes, uint32_t bar) {
  asm volatile("cp.async.bulk.shared::cluster.global.mbarrier::complete_tx::bytes [%0], [%1], %2, [%3];"
               ::"r"(dst), "l"(src), "r"(bytes), "r"(bar) : "memory");
}
__device__ __forceinline__ void bulk_store(void* dst, uint32_t src, uint32_t bytes) {
  asm volatile("cp.async.bulk.global.shared::cta.bulk_group [%0], [%1], %2;" ::"l"(dst), "r"(src), "r"(bytes) : "memory");
}
__device__ __forceinline__ void bulk_wait_read() {
  asm volatile("cp.async.bulk.commit_group;\ncp.async.bulk.wait_group.read 0;" ::: "memory");
}

__device__ __forceinline__ void publish(void* dst, uint32_t src, uint32_t bytes) {
  bulk_store(dst, src, bytes);
  bulk_wait_read();
}

__device__ __forceinline__ void wg_fence() { asm volatile("wgmma.fence.sync.aligned;" ::: "memory"); }
__device__ __forceinline__ void wg_commit() { asm volatile("wgmma.commit_group.sync.aligned;" ::: "memory"); }
template <int N> __device__ __forceinline__ void wg_wait() { asm volatile("wgmma.wait_group.sync.aligned %0;" ::"n"(N) : "memory"); }
__device__ __forceinline__ uint32_t desc_lo(uint32_t addr, uint32_t lbo) { return ((addr & 0x3FFFF) >> 4) | ((lbo >> 4) << 16); }
constexpr uint32_t desc_hi(uint32_t sbo, uint32_t swz) { return (sbo >> 4) | (swz << 30); }
constexpr uint32_t HI_SW128 = desc_hi(1024, 1), HI_SW64 = desc_hi(512, 2), HI_SW32 = desc_hi(256, 3), HI_NONE = desc_hi(128, 0);
template <int N> __device__ __forceinline__ void pin(float* d) {
#pragma unroll
  for (int i = 0; i < N; i++) asm volatile("" : "+f"(d[i])::"memory");
}

__device__ __forceinline__ uint32_t lds32(uint32_t a) {
  uint32_t v;
  asm volatile("ld.volatile.shared.u32 %0, [%1];" : "=r"(v) : "r"(a) : "memory");
  return v;
}
__device__ __forceinline__ uint2 ldg64(const void* a) {
  uint2 v;
  asm volatile("ld.global.nc.v2.u32 {%0, %1}, [%2];" : "=r"(v.x), "=r"(v.y) : "l"(a) : "memory");
  return v;
}
__device__ __forceinline__ void ldsm4(uint32_t* r, uint32_t a) {
  asm volatile("ldmatrix.sync.aligned.m8n8.x4.shared.b16 {%0, %1, %2, %3}, [%4];"
               : "=r"(r[0]), "=r"(r[1]), "=r"(r[2]), "=r"(r[3]) : "r"(a) : "memory");
}
__device__ __forceinline__ void ldsm4t(uint32_t* r, uint32_t a) {
  asm volatile("ldmatrix.sync.aligned.m8n8.x4.trans.shared.b16 {%0, %1, %2, %3}, [%4];"
               : "=r"(r[0]), "=r"(r[1]), "=r"(r[2]), "=r"(r[3]) : "r"(a) : "memory");
}
__device__ __forceinline__ uint2 lds64(uint32_t a) {
  uint2 v;
  asm volatile("ld.shared.v2.u32 {%0, %1}, [%2];" : "=r"(v.x), "=r"(v.y) : "r"(a) : "memory");
  return v;
}
__device__ __forceinline__ uint4 lds128(uint32_t a) {
  uint4 v;
  asm volatile("ld.shared.v4.u32 {%0, %1, %2, %3}, [%4];" : "=r"(v.x), "=r"(v.y), "=r"(v.z), "=r"(v.w) : "r"(a) : "memory");
  return v;
}
__device__ __forceinline__ void sts128(uint32_t a, uint32_t x, uint32_t y, uint32_t z, uint32_t w) {
  asm volatile("st.shared.v4.u32 [%0], {%1, %2, %3, %4};" ::"r"(a), "r"(x), "r"(y), "r"(z), "r"(w) : "memory");
}
__device__ __forceinline__ void stsm4(uint32_t a, const uint32_t* r) {
  asm volatile("stmatrix.sync.aligned.m8n8.x4.shared.b16 [%0], {%1, %2, %3, %4};" ::"r"(a), "r"(r[0]), "r"(r[1]), "r"(r[2]), "r"(r[3]) : "memory");
}
__device__ __forceinline__ uint32_t pack2(float lo, float hi) {
  uint32_t r;
  asm("cvt.rn.bf16x2.f32 %0, %1, %2;" : "=r"(r) : "f"(hi), "f"(lo));
  return r;
}
__device__ __forceinline__ uint32_t movm(uint32_t a) {
  uint32_t d;
  asm volatile("movmatrix.sync.aligned.m8n8.trans.b16 %0, %1;" : "=r"(d) : "r"(a));
  return d;
}
__device__ __forceinline__ uint32_t bmul(uint32_t a, uint32_t b) {
  uint32_t d;
  asm("mul.rn.bf16x2 %0, %1, %2;" : "=r"(d) : "r"(a), "r"(b));
  return d;
}
__device__ __forceinline__ uint32_t badd(uint32_t a, uint32_t b) {
  uint32_t d;
  asm("add.rn.bf16x2 %0, %1, %2;" : "=r"(d) : "r"(a), "r"(b));
  return d;
}
__device__ __forceinline__ uint32_t bfma(uint32_t a, uint32_t b, uint32_t c) {
  uint32_t d;
  asm("fma.rn.bf16x2 %0, %1, %2, %3;" : "=r"(d) : "r"(a), "r"(b), "r"(c));
  return d;
}
__device__ __forceinline__ float bf_lo(uint32_t x) { return __uint_as_float(x << 16); }
__device__ __forceinline__ float bf_hi(uint32_t x) { return __uint_as_float(x & 0xFFFF0000u); }
__device__ __forceinline__ float ex2(float x) {
  float y;
  asm("ex2.approx.ftz.f32 %0, %1;" : "=f"(y) : "f"(x));
  return y;
}
__device__ __forceinline__ float rcp(float x) {
  float y;
  asm("rcp.approx.ftz.f32 %0, %1;" : "=f"(y) : "f"(x));
  return y;
}
__device__ __forceinline__ void mma16816(float* d, uint32_t a0, uint32_t a1, uint32_t a2, uint32_t a3, uint32_t b0, uint32_t b1) {
  asm volatile("mma.sync.aligned.m16n8k16.row.col.f32.bf16.bf16.f32 {%0, %1, %2, %3}, {%4, %5, %6, %7}, {%8, %9}, {%0, %1, %2, %3};"
               : "+f"(d[0]), "+f"(d[1]), "+f"(d[2]), "+f"(d[3])
               : "r"(a0), "r"(a1), "r"(a2), "r"(a3), "r"(b0), "r"(b1));
}
__device__ __forceinline__ void mma1688(float* d, uint32_t a0, uint32_t a1, uint32_t b0) {
  asm volatile("mma.sync.aligned.m16n8k8.row.col.f32.bf16.bf16.f32 {%0, %1, %2, %3}, {%4, %5}, {%6}, {%0, %1, %2, %3};"
               : "+f"(d[0]), "+f"(d[1]), "+f"(d[2]), "+f"(d[3])
               : "r"(a0), "r"(a1), "r"(b0));
}

template <int N> struct WgRS;
template <int N> struct WgSST;
template <> struct WgRS<32> {
  template <uint32_t HB>
  static __device__ __forceinline__ void mma(float* d, const uint32_t* a, uint32_t db) {
    asm volatile("{\n.reg .pred p;\n.reg .b64 db;\nsetp.ne.b32 p, %22, 0;\n"
      "mov.b64 db, {%20, %21};\n"
      "wgmma.mma_async.sync.aligned.m64n32k16.f32.bf16.bf16 {"
      "%0, %1, %2, %3, %4, %5, %6, %7, %8, %9, %10, %11, %12, %13, %14, %15"
      "}, {%16, %17, %18, %19}, db, p, 1, 1, 1;\n}\n"
      : "+f"(d[0]), "+f"(d[1]), "+f"(d[2]), "+f"(d[3]), "+f"(d[4]), "+f"(d[5]), "+f"(d[6]), "+f"(d[7]),
        "+f"(d[8]), "+f"(d[9]), "+f"(d[10]), "+f"(d[11]), "+f"(d[12]), "+f"(d[13]), "+f"(d[14]), "+f"(d[15])
      : "r"(a[0]), "r"(a[1]), "r"(a[2]), "r"(a[3]), "r"(db), "n"(HB), "n"(1));
  }
  template <uint32_t HB>
  static __device__ __forceinline__ void set(float* d, const uint32_t* a, uint32_t db) {
    asm volatile("{\n.reg .pred p;\n.reg .b64 db;\nsetp.ne.b32 p, %22, 0;\n"
      "mov.b64 db, {%20, %21};\n"
      "wgmma.mma_async.sync.aligned.m64n32k16.f32.bf16.bf16 {"
      "%0, %1, %2, %3, %4, %5, %6, %7, %8, %9, %10, %11, %12, %13, %14, %15"
      "}, {%16, %17, %18, %19}, db, p, 1, 1, 1;\n}\n"
      : "=f"(d[0]), "=f"(d[1]), "=f"(d[2]), "=f"(d[3]), "=f"(d[4]), "=f"(d[5]), "=f"(d[6]), "=f"(d[7]),
        "=f"(d[8]), "=f"(d[9]), "=f"(d[10]), "=f"(d[11]), "=f"(d[12]), "=f"(d[13]), "=f"(d[14]), "=f"(d[15])
      : "r"(a[0]), "r"(a[1]), "r"(a[2]), "r"(a[3]), "r"(db), "n"(HB), "n"(0));
  }
};
template <> struct WgRS<64> {
  template <uint32_t HB>
  static __device__ __forceinline__ void mma(float* d, const uint32_t* a, uint32_t db) {
    asm volatile("{\n.reg .pred p;\n.reg .b64 db;\nsetp.ne.b32 p, %38, 0;\n"
      "mov.b64 db, {%36, %37};\n"
      "wgmma.mma_async.sync.aligned.m64n64k16.f32.bf16.bf16 {"
      "%0, %1, %2, %3, %4, %5, %6, %7, %8, %9, %10, %11, %12, %13, %14, %15, "
      "%16, %17, %18, %19, %20, %21, %22, %23, %24, %25, %26, %27, %28, %29, %30, %31"
      "}, {%32, %33, %34, %35}, db, p, 1, 1, 1;\n}\n"
      : "+f"(d[0]), "+f"(d[1]), "+f"(d[2]), "+f"(d[3]), "+f"(d[4]), "+f"(d[5]), "+f"(d[6]), "+f"(d[7]),
        "+f"(d[8]), "+f"(d[9]), "+f"(d[10]), "+f"(d[11]), "+f"(d[12]), "+f"(d[13]), "+f"(d[14]), "+f"(d[15]),
        "+f"(d[16]), "+f"(d[17]), "+f"(d[18]), "+f"(d[19]), "+f"(d[20]), "+f"(d[21]), "+f"(d[22]), "+f"(d[23]),
        "+f"(d[24]), "+f"(d[25]), "+f"(d[26]), "+f"(d[27]), "+f"(d[28]), "+f"(d[29]), "+f"(d[30]), "+f"(d[31])
      : "r"(a[0]), "r"(a[1]), "r"(a[2]), "r"(a[3]), "r"(db), "n"(HB), "n"(1));
  }
  template <uint32_t HB>
  static __device__ __forceinline__ void set(float* d, const uint32_t* a, uint32_t db) {
    asm volatile("{\n.reg .pred p;\n.reg .b64 db;\nsetp.ne.b32 p, %38, 0;\n"
      "mov.b64 db, {%36, %37};\n"
      "wgmma.mma_async.sync.aligned.m64n64k16.f32.bf16.bf16 {"
      "%0, %1, %2, %3, %4, %5, %6, %7, %8, %9, %10, %11, %12, %13, %14, %15, "
      "%16, %17, %18, %19, %20, %21, %22, %23, %24, %25, %26, %27, %28, %29, %30, %31"
      "}, {%32, %33, %34, %35}, db, p, 1, 1, 1;\n}\n"
      : "=f"(d[0]), "=f"(d[1]), "=f"(d[2]), "=f"(d[3]), "=f"(d[4]), "=f"(d[5]), "=f"(d[6]), "=f"(d[7]),
        "=f"(d[8]), "=f"(d[9]), "=f"(d[10]), "=f"(d[11]), "=f"(d[12]), "=f"(d[13]), "=f"(d[14]), "=f"(d[15]),
        "=f"(d[16]), "=f"(d[17]), "=f"(d[18]), "=f"(d[19]), "=f"(d[20]), "=f"(d[21]), "=f"(d[22]), "=f"(d[23]),
        "=f"(d[24]), "=f"(d[25]), "=f"(d[26]), "=f"(d[27]), "=f"(d[28]), "=f"(d[29]), "=f"(d[30]), "=f"(d[31])
      : "r"(a[0]), "r"(a[1]), "r"(a[2]), "r"(a[3]), "r"(db), "n"(HB), "n"(0));
  }
};
template <> struct WgSST<48> {
  template <uint32_t HA, uint32_t HB>
  static __device__ __forceinline__ void mma(float* d, uint32_t da, uint32_t db, int sc) {
    asm volatile("{\n.reg .pred p;\n.reg .b64 da, db;\nsetp.ne.b32 p, %28, 0;\n"
      "mov.b64 da, {%24, %25};\nmov.b64 db, {%26, %27};\n"
      "wgmma.mma_async.sync.aligned.m64n48k16.f32.bf16.bf16 {"
      "%0, %1, %2, %3, %4, %5, %6, %7, %8, %9, %10, %11, %12, %13, %14, %15, "
      "%16, %17, %18, %19, %20, %21, %22, %23"
      "}, da, db, p, 1, 1, 0, 1;\n}\n"
      : "+f"(d[0]), "+f"(d[1]), "+f"(d[2]), "+f"(d[3]), "+f"(d[4]), "+f"(d[5]), "+f"(d[6]), "+f"(d[7]),
        "+f"(d[8]), "+f"(d[9]), "+f"(d[10]), "+f"(d[11]), "+f"(d[12]), "+f"(d[13]), "+f"(d[14]), "+f"(d[15]),
        "+f"(d[16]), "+f"(d[17]), "+f"(d[18]), "+f"(d[19]), "+f"(d[20]), "+f"(d[21]), "+f"(d[22]), "+f"(d[23])
      : "r"(da), "n"(HA), "r"(db), "n"(HB), "r"(sc));
  }
};
template <> struct WgSST<80> {
  template <uint32_t HA, uint32_t HB>
  static __device__ __forceinline__ void mma(float* d, uint32_t da, uint32_t db, int sc) {
    asm volatile("{\n.reg .pred p;\n.reg .b64 da, db;\nsetp.ne.b32 p, %44, 0;\n"
      "mov.b64 da, {%40, %41};\nmov.b64 db, {%42, %43};\n"
      "wgmma.mma_async.sync.aligned.m64n80k16.f32.bf16.bf16 {"
      "%0, %1, %2, %3, %4, %5, %6, %7, %8, %9, %10, %11, %12, %13, %14, %15, "
      "%16, %17, %18, %19, %20, %21, %22, %23, %24, %25, %26, %27, %28, %29, %30, %31, "
      "%32, %33, %34, %35, %36, %37, %38, %39"
      "}, da, db, p, 1, 1, 0, 1;\n}\n"
      : "+f"(d[0]), "+f"(d[1]), "+f"(d[2]), "+f"(d[3]), "+f"(d[4]), "+f"(d[5]), "+f"(d[6]), "+f"(d[7]),
        "+f"(d[8]), "+f"(d[9]), "+f"(d[10]), "+f"(d[11]), "+f"(d[12]), "+f"(d[13]), "+f"(d[14]), "+f"(d[15]),
        "+f"(d[16]), "+f"(d[17]), "+f"(d[18]), "+f"(d[19]), "+f"(d[20]), "+f"(d[21]), "+f"(d[22]), "+f"(d[23]),
        "+f"(d[24]), "+f"(d[25]), "+f"(d[26]), "+f"(d[27]), "+f"(d[28]), "+f"(d[29]), "+f"(d[30]), "+f"(d[31]),
        "+f"(d[32]), "+f"(d[33]), "+f"(d[34]), "+f"(d[35]), "+f"(d[36]), "+f"(d[37]), "+f"(d[38]), "+f"(d[39])
      : "r"(da), "n"(HA), "r"(db), "n"(HB), "r"(sc));
  }
};
template <> struct WgSST<192> {
  template <uint32_t HA, uint32_t HB>
  static __device__ __forceinline__ void mma(float* d, uint32_t da, uint32_t db, int sc) {
    asm volatile("{\n.reg .pred p;\n.reg .b64 da, db;\nsetp.ne.b32 p, %100, 0;\n"
      "mov.b64 da, {%96, %97};\nmov.b64 db, {%98, %99};\n"
      "wgmma.mma_async.sync.aligned.m64n192k16.f32.bf16.bf16 {"
      "%0, %1, %2, %3, %4, %5, %6, %7, %8, %9, %10, %11, %12, %13, %14, %15, "
      "%16, %17, %18, %19, %20, %21, %22, %23, %24, %25, %26, %27, %28, %29, %30, %31, "
      "%32, %33, %34, %35, %36, %37, %38, %39, %40, %41, %42, %43, %44, %45, %46, %47, "
      "%48, %49, %50, %51, %52, %53, %54, %55, %56, %57, %58, %59, %60, %61, %62, %63, "
      "%64, %65, %66, %67, %68, %69, %70, %71, %72, %73, %74, %75, %76, %77, %78, %79, "
      "%80, %81, %82, %83, %84, %85, %86, %87, %88, %89, %90, %91, %92, %93, %94, %95"
      "}, da, db, p, 1, 1, 0, 1;\n}\n"
      : "+f"(d[0]), "+f"(d[1]), "+f"(d[2]), "+f"(d[3]), "+f"(d[4]), "+f"(d[5]), "+f"(d[6]), "+f"(d[7]),
        "+f"(d[8]), "+f"(d[9]), "+f"(d[10]), "+f"(d[11]), "+f"(d[12]), "+f"(d[13]), "+f"(d[14]), "+f"(d[15]),
        "+f"(d[16]), "+f"(d[17]), "+f"(d[18]), "+f"(d[19]), "+f"(d[20]), "+f"(d[21]), "+f"(d[22]), "+f"(d[23]),
        "+f"(d[24]), "+f"(d[25]), "+f"(d[26]), "+f"(d[27]), "+f"(d[28]), "+f"(d[29]), "+f"(d[30]), "+f"(d[31]),
        "+f"(d[32]), "+f"(d[33]), "+f"(d[34]), "+f"(d[35]), "+f"(d[36]), "+f"(d[37]), "+f"(d[38]), "+f"(d[39]),
        "+f"(d[40]), "+f"(d[41]), "+f"(d[42]), "+f"(d[43]), "+f"(d[44]), "+f"(d[45]), "+f"(d[46]), "+f"(d[47]),
        "+f"(d[48]), "+f"(d[49]), "+f"(d[50]), "+f"(d[51]), "+f"(d[52]), "+f"(d[53]), "+f"(d[54]), "+f"(d[55]),
        "+f"(d[56]), "+f"(d[57]), "+f"(d[58]), "+f"(d[59]), "+f"(d[60]), "+f"(d[61]), "+f"(d[62]), "+f"(d[63]),
        "+f"(d[64]), "+f"(d[65]), "+f"(d[66]), "+f"(d[67]), "+f"(d[68]), "+f"(d[69]), "+f"(d[70]), "+f"(d[71]),
        "+f"(d[72]), "+f"(d[73]), "+f"(d[74]), "+f"(d[75]), "+f"(d[76]), "+f"(d[77]), "+f"(d[78]), "+f"(d[79]),
        "+f"(d[80]), "+f"(d[81]), "+f"(d[82]), "+f"(d[83]), "+f"(d[84]), "+f"(d[85]), "+f"(d[86]), "+f"(d[87]),
        "+f"(d[88]), "+f"(d[89]), "+f"(d[90]), "+f"(d[91]), "+f"(d[92]), "+f"(d[93]), "+f"(d[94]), "+f"(d[95])
      : "r"(da), "n"(HA), "r"(db), "n"(HB), "r"(sc));
  }
};

struct FftConst {
  uint32_t f[2][4], fi[4][4];
  uint32_t ta[2][2], tb[2][2];
};
__device__ __forceinline__ void cis(int m, float scale, float& c, float& s) {
  const float a = (float)m * (-6.283185307179586f * scale);
  c = __cosf(a);
  s = __sinf(a);
}
__device__ __forceinline__ void fft_tables(uint32_t (&v)[12], int tw) {
  const int row = tw >> 2, ch = tw & 3;
#pragma unroll
  for (int i = 0; i < 4; i++) {
    float c[2], s[2], x[2];
#pragma unroll
    for (int e = 0; e < 2; e++) {
      cis((((32 * (8 * ch + 2 * i + e) + 15) * (4 * row - 63) + 2048) & 4095) - 2048, 1.f / 4096, c[e], s[e]);
      float gc, gs;
      cis((((row & 15) * (8 * (ch & 1) + 2 * i + e) + 8) & 15) - 8, 1.f / 16, gc, gs);
      x[e] = (row >> 4) == (ch >> 1) ? gc : (ch >> 1) ? gs : -gs;
    }
    v[i] = pack2(c[0] * 0.125f, c[1] * 0.125f);
    v[4 + i] = pack2(s[0] * 0.125f, s[1] * 0.125f);
    v[8 + i] = pack2(x[0], x[1]);
  }
#pragma unroll
  for (int i = 0; i < 12; i++) asm volatile("" : "+r"(v[i]));
}
__device__ __forceinline__ void fft_tables_store(const uint32_t (&v)[12], uint32_t sb, int tw) {
  const int row = tw >> 2;
  const uint32_t x = ((tw ^ (row >> 1)) & 3) << 4, a = sb + OFF_FT + (16 * (row >> 3) + (row & 7)) * 64 + x;
  sts128(a, v[0], v[1], v[2], v[3]);
  sts128(a + 512, v[4], v[5], v[6], v[7]);
  sts128(sb + OFF_GT + row * 64 + x, v[8], v[9], v[10], v[11]);
}
__device__ __forceinline__ void fft_twiddles(uint32_t (&v)[2], int tw) {
  float a[2], s[2];
#pragma unroll
  for (int i = 0; i < 2; i++) {
    float c;
    cis((2 * (2 * (tw & 3) + i) - 15) * (4 * (tw >> 2) - 63), 1.f / 4096, c, s[i]);
    a[i] = __fdividef(-s[i], 1.f + c);
  }
  v[0] = pack2(a[0], a[1]);
  v[1] = pack2(s[0], s[1]);
  asm volatile("" : "+r"(v[0]), "+r"(v[1]));
}
__device__ __forceinline__ void fft_matrices(FftConst& k, uint32_t sb, int w, int lane) {
  const uint32_t x = (lane >> 1) & 3;
  const uint2 t0 = lds64(sb + OFF_TT + 256 * w + 8 * lane), t1 = lds64(sb + OFF_TT + 256 * w + 8 * (lane ^ 3));
  k.ta[0][0] = t0.x;
  k.tb[0][0] = t0.y;
  k.ta[1][1] = __byte_perm(t1.x, 0, 0x1032);
  k.tb[1][1] = __byte_perm(t1.y, 0, 0x1032);
#pragma unroll
  for (int j = 0; j < 2; j++) {
    k.ta[1 - j][j] = k.ta[j][j] ^ 0x80008000u;
    k.tb[1 - j][j] = k.tb[j][j] ^ 0x80008000u;
    asm volatile("" : "+r"(k.ta[0][j]), "+r"(k.tb[0][j]), "+r"(k.ta[1][j]), "+r"(k.tb[1][j]));
  }
#pragma unroll
  for (int i = 0; i < 2; i++) {
    ldsm4(k.f[i], sb + OFF_FT + (16 * w + (lane & 15)) * 64 + (((2 * i + (lane >> 4)) ^ x) << 4));
    ldsm4t(k.fi[i], sb + OFF_FT + (32 * i + lane) * 64 + ((w ^ x) << 4));
#pragma unroll
    for (int j = 0; j < 4; j++) {
      k.fi[2 + i][j] = (j & 1) ? k.fi[i][j - 1] ^ 0x80008000u : k.fi[i][j + 1];
      asm volatile("" : "+r"(k.fi[2 + i][j]));
    }
  }
}
__device__ __forceinline__ void rot(uint32_t& x, uint32_t& y, uint32_t a, uint32_t b) {
  x = bfma(a, y, x);
  y = bfma(b, x, y);
  x = bfma(a, y, x);
}
__device__ __forceinline__ void twiddle_fwd(uint32_t (&a)[4][4], float* d, const FftConst& k) {
#pragma unroll
  for (int q = 0; q < 4; q++)
#pragma unroll
    for (int j = 0; j < 2; j++) {
      const float* x = d + 8 * q + 4 * j;
      uint32_t re = pack2(x[0], x[1]), im = pack2(x[2], x[3]);
      rot(re, im, k.ta[0][j], k.tb[0][j]);
      a[q & 2][2 * j + (q & 1)] = re;
      a[(q & 2) + 1][2 * j + (q & 1)] = im;
    }
}
__device__ __forceinline__ void g_step(float* d, const uint32_t (&a)[4][4], uint32_t dre, uint32_t dim) {
  WgRS<32>::set<HI_SW64>(d, a[0], dre);
  WgRS<32>::set<HI_SW64>(d + 16, a[2], dre);
  WgRS<32>::mma<HI_SW64>(d, a[1], dim);
  WgRS<32>::mma<HI_SW64>(d + 16, a[3], dim);
  wg_commit();
}

__device__ __forceinline__ void products(uint32_t (&a)[4][4], const float* H, const float* U, int p) {
#pragma unroll
  for (int j = 0; j < 2; j++)
#pragma unroll
    for (int m = 2 * p; m < 2 * p + 2; m++) {
      float pr[2], pi[2];
#pragma unroll
      for (int x = 0; x < 2; x++)
#pragma unroll
        for (int q = 0; q <= m; q++) {
          const int ih = 16 * (q >> 1) + 2 * (q & 1) + 4 * j + x, iu = 16 * ((m - q) >> 1) + 2 * ((m - q) & 1) + 4 * j + x;
          pr[x] = q ? fmaf(H[ih], U[iu], pr[x]) : H[ih] * U[iu];
          pi[x] = q ? fmaf(H[ih], U[iu + 8], pi[x]) : H[ih] * U[iu + 8];
          pr[x] = fmaf(-H[ih + 8], U[iu + 8], pr[x]);
          pi[x] = fmaf(H[ih + 8], U[iu], pi[x]);
        }
      a[m & 2][2 * j + (m & 1)] = pack2(pr[0], pr[1]);
      a[(m & 2) + 1][2 * j + (m & 1)] = pack2(pi[0], pi[1]);
    }
}

__device__ __forceinline__ void prep_gate(const Params& p, uint32_t sb, int b, int w, int lane) {
  uint2 gw[5], x[4][5];
#pragma unroll
  for (int j = 0; j < 5; j++) gw[j] = ldg64(reinterpret_cast<const uint2*>(p.gate_w) + lane + 32 * j);
#pragma unroll
  for (int i = 0; i < 4; i++)
#pragma unroll
    for (int j = 0; j < 5; j++)
      x[i][j] = ldg64(reinterpret_cast<const uint2*>(p.q) + (16 * b + 4 * w + i) * (DIM / 4) + lane + 32 * j);
  float s[4];
#pragma unroll
  for (int i = 0; i < 4; i++) {
    s[i] = 0.f;
#pragma unroll
    for (int j = 0; j < 5; j++) {
      const uint32_t m0 = bmul(x[i][j].x, gw[j].x), m1 = bmul(x[i][j].y, gw[j].y);
      s[i] += (bf_lo(m0) + bf_hi(m0)) + (bf_lo(m1) + bf_hi(m1));
    }
  }
  const bool h = lane & 16, q = lane & 8;
  const float a = (h ? s[2] : s[0]) + __shfl_xor_sync(0xffffffffu, h ? s[0] : s[2], 16);
  const float c = (h ? s[3] : s[1]) + __shfl_xor_sync(0xffffffffu, h ? s[1] : s[3], 16);
  float z = (q ? c : a) + __shfl_xor_sync(0xffffffffu, q ? a : c, 8);
#pragma unroll
  for (int o = 4; o > 0; o >>= 1) z += __shfl_xor_sync(0xffffffffu, z, o);
  z = bf_lo(pack2(z, 0.f));
  z = bf_lo(pack2(__fdividef(1.f, 1.f + __expf(-z)), 0.f));
  mbar_wait(sb + OFF_BAR + 8 * B_S3, 0);
  if ((lane & 7) == 0) asm volatile("st.shared.f32 [%0], %1;" ::"r"(sb + OFF_GATE + 64 * (b & 7) + 16 * w + (lane >> 1)), "f"(z) : "memory");
  fence_async_smem();
}

__device__ __forceinline__ void conv_channel(const FftConst& k, const Params& p, int b, uint32_t sb, int c, int wg, int w, int lane) {
  const uint32_t cb = sb + off_ch(c), bars = sb + OFF_BAR;
  const uint32_t du = desc_lo(cb, 1024), dg = desc_lo(sb + OFF_GT, 16), dz = desc_lo(cb + U_BYTES, 16);
  float U[32], H[32];
  uint32_t a[4][4], e[4][4];
  const float dv = __uint_as_float(lds32(sb + OFF_D + 4 * c));
  wg_fence();
  WgRS<64>::set<HI_SW32>(H, k.f[0], du + 256);
  WgRS<64>::mma<HI_SW32>(H, k.f[1], du + 256 + 32);
  wg_commit();
  wg_wait<0>();
  pin<32>(H);
  twiddle_fwd(a, H, k);
  if (G_IN && c == 0) {
    if (G_IN == 1) mbar_wait(bars + 8 * B_USIG, 0);
    prep_gate(p, sb, b, w, lane);
    __syncwarp();
    if (lane == 0) mbar_arrive(bars + 8 * B_GATE);
    TSIF(w == 0, 72);
  }
  mbar_wait(bars + 8 * (B_U + (c < 3 ? c : 3)), 0);
  TSM(w == 0 && c < 3, 7 + wg);
  wg_fence();
  WgRS<64>::set<HI_SW32>(U, k.f[0], du);
  WgRS<64>::mma<HI_SW32>(U, k.f[1], du + 32);
  wg_commit();
  g_step(H, a, dg, dg + 64);
  wg_wait<1>();
  pin<32>(U);
  twiddle_fwd(e, U, k);
  wg_fence();
  g_step(U, e, dg, dg + 64);
  wg_wait<0>();
  pin<32>(U);
  pin<32>(H);
#pragma unroll
  for (int j = 0; j < 4; j++) H[4 * (j >> 1) + (j & 1)] += dv;
  float V[32];
#pragma unroll
  for (int p = 0; p < 2; p++) {
    products(a, H, U, p);
    wg_fence();
    WgRS<32>::set<HI_SW64>(V + 16 * p, a[2 * p], dg + 64);
    WgRS<32>::mma<HI_SW64>(V + 16 * p, a[2 * p + 1], dg);
    wg_commit();
  }
  const uint32_t za = cb + U_BYTES + (8 * w + (lane & 7)) * 128 + (((lane >> 3) ^ (lane & 7)) << 4);
  const uint32_t ya = cb + (lane >> 4) * 1024 + (8 * w + (lane & 7)) * 32 + ((((lane >> 3) ^ (lane >> 2)) & 1) << 4);
  wg_sync(1 + wg);
#pragma unroll
  for (int p = 0; p < 2; p++) {
    if (p == 0) wg_wait<1>();
    else wg_wait<0>();
    pin<16>(V + 16 * p);
#pragma unroll
    for (int i = 0; i < 4; i++) {
      const int j = i & 1;
      const float* x = V + 16 * p + 4 * j + (i & 2);
      e[p][i] = pack2(x[8], x[9]);
      e[2 + p][i] = pack2(x[0], x[1]);
      rot(e[p][i], e[2 + p][i], k.ta[1][j], k.tb[1][j]);
    }
    stsm4(za ^ (64 * p), e[p]);
    stsm4((za ^ (64 * p)) + 4096, e[2 + p]);
  }
  fence_async_smem();
  wg_sync(1 + wg);
  wg_fence();
  WgRS<64>::set<HI_SW128>(H, k.fi[0], dz);
#pragma unroll
  for (int ks = 1; ks < 4; ks++) WgRS<64>::mma<HI_SW128>(H, k.fi[ks], dz + 128 * ks);
  wg_commit();
  wg_wait<0>();
  pin<32>(H);
  if (lane == 0) mbar_arrive(bars + 8 * B_CVD);
  TSIF(w == 0, 88 + c);
#pragma unroll
  for (int j = 0; j < 8; j++)
    a[j >> 2][j & 3] = j < 2 ? pack2(H[4 * j], H[4 * j + 1]) : pack2(H[4 * j] + H[4 * j - 6], H[4 * j + 1] + H[4 * j - 5]);
  stsm4(ya, a[0]);
  stsm4(ya + 2048, a[1]);
  fence_async_smem();
  __syncwarp();
}

__device__ __forceinline__ void prep_slab(uint4* res, const uint2* sw, uint32_t sb, int slab, int w, int lane) {
  const int t = lane & 3, tp = (lane & 7) >> 1, pos = 8 * tp + 2 * (((lane >> 3) + tp) & 3) + (lane & 1);
  const uint32_t base = sb + OFF_KVS + slab * KVS_BYTES + pos * 128;
  uint32_t kk[2][4][4], vv[2][4];
  mbar_wait(sb + OFF_BAR + 8 * (B_KV + slab), 0);
#pragma unroll
  for (int h = 0; h < 2; h++) {
#pragma unroll
    for (int j = 0; j < 4; j++) {
      const uint32_t a = base + 128 * j;
      ldsm4t(kk[h][j], a + (((w + 4 * h) ^ ((a >> 7) & 7)) << 4));
    }
    const uint32_t a = base + KVS_V;
    ldsm4t(vv[h], a + (((w + 4 * h) ^ ((a >> 7) & 7)) << 4));
  }
#pragma unroll
  for (int h = 0; h < 2; h++) {
    uint32_t (&k)[4][4] = kk[h];
    uint32_t (&v)[4] = vv[h];
    const uint32_t w0 = __byte_perm(sw[h].x, 0, 0x1010), w1 = __byte_perm(sw[h].x, 0, 0x3232);
    const uint32_t w2 = __byte_perm(sw[h].y, 0, 0x1010), w3 = __byte_perm(sw[h].y, 0, 0x3232);
#pragma unroll
    for (int m = 0; m < 4; m++)
      v[m] = bmul(badd(badd(badd(bmul(k[0][m], w3), bmul(k[1][m], w2)), bmul(k[2][m], w1)), bmul(k[3][m], w0)), v[m]);
    uint32_t a[4];
#pragma unroll
    for (int m = 0; m < 4; m++) a[m] = (t & 1) ? v[(m + 3) & 3] : v[m];
    res[h] = (t & 2) ? make_uint4(a[2], a[3], a[0], a[1]) : make_uint4(a[0], a[1], a[2], a[3]);
  }
}

__device__ __forceinline__ uint32_t bmax(uint32_t a, uint32_t b) {
  uint32_t d;
  asm("max.bf16x2 %0, %1, %2;" : "=r"(d) : "r"(a), "r"(b));
  return d;
}
__device__ __forceinline__ void softmax_two(const float (&l)[2][2], uint32_t& p0, uint32_t& p1) {
  constexpr float kScale = 0.22360679774997896f, kLog2e = 1.4426950408889634f;
  const uint32_t r0 = pack2(l[0][0], l[1][0]), r1 = pack2(l[0][1], l[1][1]);
  const uint32_t x0 = pack2(bf_lo(r0) * kScale, bf_hi(r0) * kScale), x1 = pack2(bf_lo(r1) * kScale, bf_hi(r1) * kScale);
  uint32_t m = bmax(x0, x1);
  m = bmax(m, __shfl_xor_sync(0xffffffffu, m, 1));
  m = bmax(m, __shfl_xor_sync(0xffffffffu, m, 2));
  const float m0 = bf_lo(m) * kLog2e, m1 = bf_hi(m) * kLog2e;
  p0 = pack2(ex2(bf_lo(x0) * kLog2e - m0), ex2(bf_lo(x1) * kLog2e - m0));
  p1 = pack2(ex2(bf_hi(x0) * kLog2e - m1), ex2(bf_hi(x1) * kLog2e - m1));
}

__device__ __forceinline__ void halo_read(uint32_t (&kpv)[10], uint32_t (&vpv)[10], uint32_t (&tg)[7], const uint4* hp) {
#pragma unroll
  for (int j = 0; j < 7; j++) {
    uint32_t x0, x1, x2;
    asm volatile("ld.relaxed.gpu.global.v4.u32 {%0, %1, %2, %3}, [%4];"
                 : "=r"(x0), "=r"(x1), "=r"(x2), "=r"(tg[j]) : "l"(hp + 32 * j) : "memory");
    if (j < 4) kpv[3 * j] = x0; else vpv[3 * j - 10] = x0;
    if (j < 3) kpv[3 * j + 1] = x1; else vpv[3 * j - 9] = x1;
    if (j < 3) kpv[3 * j + 2] = x2; else if (j < 6) vpv[3 * j - 8] = x2;
  }
}

template <int ROT>
__device__ __forceinline__ void pack_qkv(const float* acc, uint32_t (&qlo)[10], uint32_t (&qhi)[10], uint32_t (&klo)[10],
                                         uint32_t (&khi)[10], uint32_t (&vlo)[10], uint32_t (&vhi)[10]) {
#pragma unroll
  for (int j = 0; j < 10; j++) {
    const int x = (j + ROT) % 10, tq = x < 8 ? x : 16 + x, tk = x < 8 ? 8 + x : 18 + x, tv = x < 8 ? 16 + x : 20 + x;
    khi[j] = pack2(acc[4 * tk + 2], acc[4 * tk + 3]);
    vhi[j] = movm(pack2(acc[4 * tv + 2], acc[4 * tv + 3]));
    qlo[j] = pack2(acc[4 * tq], acc[4 * tq + 1]);
    qhi[j] = pack2(acc[4 * tq + 2], acc[4 * tq + 3]);
    klo[j] = pack2(acc[4 * tk], acc[4 * tk + 1]);
    vlo[j] = pack2(acc[4 * tv], acc[4 * tv + 1]);
    asm volatile("" : "+r"(khi[j]), "+r"(qlo[j]), "+r"(qhi[j]), "+r"(klo[j]), "+r"(vlo[j]));
  }
}

template <int ROT> __device__ __forceinline__ void halo_send(const float* acc, uint4* ho, uint32_t tag) {
#pragma unroll
  for (int j = 0; j < 7; j++) {
    uint32_t x[3];
#pragma unroll
    for (int e = 0; e < 3; e++) {
      const int i = 3 * j + e, y = (i % 10 + ROT) % 10, tk = y < 8 ? 8 + y : 18 + y, tv = y < 8 ? 16 + y : 20 + y;
      x[e] = i < 10 ? pack2(acc[4 * tk + 2], acc[4 * tk + 3]) : i < 20 ? movm(pack2(acc[4 * tv + 2], acc[4 * tv + 3])) : 0u;
    }
    asm volatile("st.relaxed.gpu.global.v4.u32 [%0], {%1, %2, %3, %4};" ::"l"(ho + 32 * j), "r"(x[0]), "r"(x[1]), "r"(x[2]), "r"(tag) : "memory");
  }
}

__device__ __forceinline__ void attention(float* acc, uint32_t sb, int b, int par, int w, int lane, uint32_t tag, FftConst& fc) {
  const int g = lane >> 2, t = lane & 3;
  uint32_t klo[10], khi[10], vlo[10], vhi[10], qlo[10], qhi[10], kpv[10], vpv[10];
  if (w == 3 && b < NCTA - 8) {
    uint4* ho = g_halo + (b * 2 + par) * 224 + lane;
    if (tail_first(b & 7)) halo_send<8>(acc, ho, tag);
    else halo_send<0>(acc, ho, tag);
    TSIF(par == 0, 76);
    pin<120>(acc);
  }
  if (tail_first(b & 7)) pack_qkv<8>(acc, qlo, qhi, klo, khi, vlo, vhi);
  else pack_qkv<0>(acc, qlo, qhi, klo, khi, vlo, vhi);
  const uint32_t xa = sb + OFF_KVX + (par * 3) * 2560 + lane * 16;
  if (w < 3) {
    sts128(xa + w * 2560, khi[0], khi[1], khi[2], khi[3]);
    sts128(xa + w * 2560 + 512, khi[4], khi[5], khi[6], khi[7]);
    sts128(xa + w * 2560 + 1024, khi[8], khi[9], vhi[0], vhi[1]);
    sts128(xa + w * 2560 + 1536, vhi[2], vhi[3], vhi[4], vhi[5]);
    sts128(xa + w * 2560 + 2048, vhi[6], vhi[7], vhi[8], vhi[9]);
  }
  TSIF(par == 0 && w == 1, 64);
#pragma unroll
  for (int j = 0; j < 10; j++) vlo[j] = movm(vlo[j]);
  const bool far0 = 2 * t > g, far1 = 2 * t + 1 > g;
  const uint32_t mfar = (far0 ? 0x0000FFFFu : 0u) | (far1 ? 0xFFFF0000u : 0u);
  float slo[4][2], lg[2][2];
  uint32_t phi[4], plo[4], qml[4], qmh[4];
#pragma unroll
  for (int h = 0; h < 4; h++) {
    const int f = h == 0 ? 0 : h == 1 ? 3 : h == 2 ? 5 : 8, hf = h < 2 ? 2 : 7;
    const bool mine = (h & 1) ? t >= 2 : t < 2;
    qml[h] = mine ? qlo[hf] : 0u;
    qmh[h] = mine ? qhi[hf] : 0u;
    float a[4] = {0.f, 0.f, 0.f, 0.f}, c[4] = {0.f, 0.f, 0.f, 0.f};
    mma16816(a, qlo[f], qhi[f], qlo[f + 1], qhi[f + 1], klo[f], klo[f + 1]);
    mma16816(c, qlo[f], qhi[f], qlo[f + 1], qhi[f + 1], khi[f], khi[f + 1]);
    mma1688(a, qml[h], qmh[h], klo[hf]);
    mma1688(c, qml[h], qmh[h], khi[hf]);
    slo[h][0] = a[0];
    slo[h][1] = a[1];
    lg[h & 1][0] = far0 ? a[2] : c[2];
    lg[h & 1][1] = far1 ? a[3] : c[3];
    if (h & 1) softmax_two(lg, phi[h - 1], phi[h]);
  }
  TSIF(par == 0 && w == 1, 65);
  wg_sync(1 + par);
  TSIF(par == 0 && w == 1, 66);
  const bool nohist = (w == 0) && (b < 8);
  const uint4* hp = g_halo + ((b - 8) * 2 + par) * 224 + lane;
  uint32_t tg[7];
  if (w > 0) {
    const uint4 v0 = lds128(xa + (w - 1) * 2560), v1 = lds128(xa + (w - 1) * 2560 + 512), v2 = lds128(xa + (w - 1) * 2560 + 1024);
    const uint4 v3 = lds128(xa + (w - 1) * 2560 + 1536), v4 = lds128(xa + (w - 1) * 2560 + 2048);
    kpv[0] = v0.x; kpv[1] = v0.y; kpv[2] = v0.z; kpv[3] = v0.w; kpv[4] = v1.x; kpv[5] = v1.y; kpv[6] = v1.z; kpv[7] = v1.w;
    kpv[8] = v2.x; kpv[9] = v2.y; vpv[0] = v2.z; vpv[1] = v2.w; vpv[2] = v3.x; vpv[3] = v3.y; vpv[4] = v3.z; vpv[5] = v3.w;
    vpv[6] = v4.x; vpv[7] = v4.y; vpv[8] = v4.z; vpv[9] = v4.w;
  } else if (nohist) {
#pragma unroll
    for (int j = 0; j < 10; j++) kpv[j] = vpv[j] = 0u;
  } else {
    TSIF(par == 0, 77);
    halo_read(kpv, vpv, tg, hp);
  }
  if (w == 0 && !nohist) {
    int spins = 0;
    while (true) {
      bool ok = true;
#pragma unroll
      for (int j = 0; j < 7; j++) ok = ok && tg[j] == tag;
      if (__all_sync(0xffffffffu, ok) || ++spins > SPIN_LIMIT) break;
      halo_read(kpv, vpv, tg, hp);
    }
    TSIF(par == 0, 79);
  }
#pragma unroll
  for (int h = 0; h < 4; h++) {
    const int f = h == 0 ? 0 : h == 1 ? 3 : h == 2 ? 5 : 8, hf = h < 2 ? 2 : 7;
    float a[4] = {0.f, 0.f, 0.f, 0.f};
    mma16816(a, qlo[f], qhi[f], qlo[f + 1], qhi[f + 1], kpv[f], kpv[f + 1]);
    mma1688(a, qml[h], qmh[h], kpv[hf]);
    const float ninf = __int_as_float(0xff800000);
    lg[h & 1][0] = far0 ? (nohist ? ninf : a[0]) : slo[h][0];
    lg[h & 1][1] = far1 ? (nohist ? ninf : a[1]) : slo[h][1];
    if (h & 1) softmax_two(lg, plo[h - 1], plo[h]);
  }
  TSIF(par == 0 && w <= 1, 67 + w);
  mbar_wait(sb + OFF_BAR + 8 * B_HA, 0);
  fft_matrices(fc, sb, w, lane);
  uint32_t ov[20];
#pragma unroll
  for (int hp = 0; hp < 2; hp++) {
    const int hf = hp ? 7 : 2;
    float sh[4] = {0.f, 0.f, 0.f, 0.f}, i0 = 0.f, i1 = 0.f;
#pragma unroll
    for (int e = 0; e < 2; e++) {
      const int h = 2 * hp + e, f = h == 0 ? 0 : h == 1 ? 3 : h == 2 ? 5 : 8;
      const uint32_t a0 = plo[h] & mfar, a2 = plo[h] & ~mfar, a3 = phi[h] & mfar, c1 = phi[h] & ~mfar;
      float sum[4] = {0.f, 0.f, 0.f, 0.f};
      mma1688(sum, plo[h], phi[h], 0x3F803F80u);
      const float r0 = rcp(sum[0]), r1 = rcp(sum[2]);
#pragma unroll
      for (int j = f; j < f + 2; j++) {
        float o[4] = {0.f, 0.f, 0.f, 0.f};
        mma16816(o, a0, 0u, a2, a3, vpv[j], vlo[j]);
        mma1688(o, 0u, c1, vhi[j]);
        ov[2 * j] = pack2(o[0] * r0, o[1] * r0);
        ov[2 * j + 1] = pack2(o[2] * r1, o[3] * r1);
      }
      const bool mine = e ? g >= 4 : g < 4;
      mma16816(sh, a0, 0u, a2, a3, mine ? vpv[hf] : 0u, mine ? vlo[hf] : 0u);
      mma1688(sh, 0u, c1, mine ? vhi[hf] : 0u);
      if (e == 0 || t >= 2) {
        i0 = r0;
        i1 = r1;
      }
    }
    ov[2 * hf] = pack2(sh[0] * i0, sh[1] * i0);
    ov[2 * hf + 1] = pack2(sh[2] * i1, sh[3] * i1);
  }
  TS(32 + 4 * par + w);
  mbar_wait(sb + OFF_BAR + 8 * B_P1, 0);
  const uint32_t oa = sb + OFF_OA + (lane >> 4) * 2048 + (32 * w + 2 * (lane & 15) + par) * 16;
#pragma unroll
  for (int j = 0; j < 5; j++) stsm4(oa + 4096 * j, ov + 4 * j);
  TSIF(par == 0 && w == 0, 120);
  fence_async_smem();
  TSIF(par == 0 && w == 0, 121);
  __syncwarp();
  if (lane == 0) mbar_arrive(sb + OFF_BAR + 8 * B_ATTN);
  TSM(w == 0 || w == 2, 122 + par + (w == 2 ? 3 : 0));
}

struct Maps {
  CUtensorMap x, wm, wt, k, v, y, wo, qm, qt, om, ot, yl, ol, wh;
};

__device__ __forceinline__ void load_stage(uint32_t sb, int kb, int b, const Maps& m) {
  const uint32_t st = sb + (kb & 3) * STAGE_BYTES, bar = sb + OFF_BAR + 8 * (B_FULL1 + (kb & 3));
  const int r = b >> 3, hg = b & 7, slab = kb - KV_KB;
  const bool kv = slab >= 0 && slab < 5;
  const uint32_t kbar = sb + OFF_BAR + 8 * (B_KV + slab), dst = sb + OFF_KVS + slab * KVS_BYTES;
  mbar_expect_tx(bar, STAGE_BYTES);
  if (kv) mbar_expect_tx(kbar, KVS_BYTES);
  tma_3d(st, &m.x, 64 * kb, 64 * r, 0, bar);
  tma_3d(st + ST_W, &m.wm, 80 * hg + (tail_first(hg) ? 16 : 0), 64 * kb, 0, bar);
  tma_3d(st + ST_WT, &m.wt, 80 * hg + (tail_first(hg) ? 0 : 64), 64 * kb, 0, bar);
  if (kv) tma_3d(dst, &m.k, 0, 32 * (b >> 1) - 3, 2 * slab + (b & 1), kbar);
  if (kv) tma_3d(dst + KVS_V, &m.v, 0, 32 * (b >> 1), 2 * slab + (b & 1), kbar);
}

__global__ void __launch_bounds__(NTHR, 1) fused_kernel(const __grid_constant__ Maps m, const Params p) {
  extern __shared__ __align__(1024) uint8_t smem[];
  const uint32_t sb = (uint32_t)__cvta_generic_to_shared(smem);
  const uint32_t bars = sb + OFF_BAR;
  const int tid = threadIdx.x, lane = tid & 31;
  int b = blockIdx.x;
  b = (((b & 63) >> 3) * 2 + (b & 1)) * 8 + (((b < 64 ? 0x6521 : 0x7430) >> (4 * ((b >> 1) & 3))) & 7);
  const int r = b >> 3, hg = b & 7;

  if (tid == T_ISSUE) {
    TSM(true, 0);
#pragma unroll
    for (int i = 0; i < 4; i++) mbar_init(bars + 8 * (B_F0 + i), 1);
    fence_async_smem();
#pragma unroll
    for (int i = 0; i < 4; i++) {
      mbar_expect_tx(bars + 8 * (B_F0 + i), (i ? 0 : ST_W) + 6144);
      if (i == 0) tma_3d(sb, &m.x, 0, 64 * r, 0, bars + 8 * B_F0);
      tma_3d(sb + ST_W + 6144 * i, &m.wh, 80 * hg + (tail_first(hg) ? 16 : 0), 16 * i, 0, bars + 8 * (B_F0 + i));
    }
#pragma unroll
    for (int i = 0; i < 4; i++) mbar_init(bars + 8 * (B_FULL1 + i), 1);
    fence_async_smem();
    mbar_expect_tx(bars + 8 * B_FULL1, STAGE_BYTES - ST_WT);
    tma_3d(sb + ST_WT, &m.wt, 80 * hg + (tail_first(hg) ? 0 : 64), 0, 0, bars + 8 * B_FULL1);
    load_stage(sb, 1, b, m);
  } else if (tid == T_INIT) {
#pragma unroll
    for (int i = 0; i < B_F0; i++) mbar_init(bars + 8 * i, i < B_GATE ? 8 : i < B_CVD ? 4 : i == B_CVD ? 20 : 1);
    fence_async_smem();
  }
  const int warp = __shfl_sync(0xffffffffu, tid >> 5, 0), wg = warp >> 2, w = warp & 3;
  __syncthreads();

  if (wg == 3) {
    asm volatile("setmaxnreg.dec.sync.aligned.u32 56;");
    if (w == 0) {
      if (lane == 0) {
#pragma unroll 1
        for (int kb = 2; kb < 10; kb++) {
          if (kb >= 4) mbar_wait(bars + 8 * (kb == 7 ? B_E3 : B_EMPTY1 + (kb & 3)), (kb >> 3) & 1);
          TSIF(kb >= 4, 44 + kb);
          load_stage(sb, kb, b, m);
          TSIF(kb == 3, 60);
          if (kb == 9) mbar_arrive(bars + 8 * B_LAST);
        }
        mbar_wait(bars + 8 * B_WOP, 0);
        mbar_wait(bars + 8 * B_EPOCH, 0);
        flag_wait(g_cnt + C_W + 32 * hg, (lds32(sb + OFF_EPOCH) + 1) * 16);
        TS(30);
#pragma unroll 1
        for (int j = 0; j < 8; j++) {
          if (j >= 6) mbar_wait(bars + 8 * (B_EMPTY2 + j - 6), 0);
          if (j == 4) mbar_wait(bars + 8 * B_ORB, 0);
          TSIF(j >= 6, 100 + j);
          mbar_expect_tx(bars + 8 * (B_FULL2 + j), j == 0 ? WO_BYTES : j == 5 ? O_BYTES + WO_BYTES + 512 : O_BYTES + WO_BYTES);
          bulk_load(sb + off_w(j), g_WO + (hg * 8 + step_src(hg, j)) * 800, WO_BYTES, bars + 8 * (B_FULL2 + j));
        }
        mbar_wait(bars + 8 * (B_EMPTY2 + 3), 0);
        mbar_expect_tx(bars + 8 * B_QF, O_BYTES);
        tma_2d(sb + OFF_QS, &m.qm, 80 * hg, 128 * r, bars + 8 * B_QF);
        tma_2d(sb + OFF_QT, &m.qt, 80 * hg + 64, 128 * r, bars + 8 * B_QF);
      }
    } else if (w == 1) {
      unsigned epoch = 0;
      if (lane == 0) {
        epoch = atomicAdd(g_cnt + C_LAUNCH, 1u) / NCTA;
        asm volatile("st.shared.u32 [%0], %1;" ::"r"(sb + OFF_EPOCH), "r"(epoch) : "memory");
        mbar_arrive(bars + 8 * B_EPOCH);
        mbar_wait(bars + 8 * B_KVD, 0);
        mbar_expect_tx(bars + 8 * B_HB, 5 * 4096);
#pragma unroll 1
        for (int c = 0; c < 5; c++) {
          if (c == 3) mbar_wait(bars + 8 * B_S3, 0);
          bulk_load(sb + off_ch(c) + U_BYTES, p.ssm_k + (5 * b + c) * SEQ, 4096, bars + 8 * B_HB);
        }
#pragma unroll
        for (int c = 0; c < 4; c++) mbar_expect_tx(bars + 8 * (B_U + c), c < 3 ? U_BYTES : 2 * U_BYTES);
        const uint4* usrc = g_U + 5 * b * U_PITCH;
        mbar_wait(bars + 8 * B_USIG, 0);
        flag_wait(g_cnt + C_PREP + 32 * (b & 15), (epoch + 1) * NCTA);
        TS(23);
#pragma unroll
        for (int c = 0; c < 5; c++) {
          if (c == 3) mbar_wait(bars + 8 * (B_U + 2), 0);
          bulk_load(sb + off_ch(c), usrc + c * U_PITCH, U_BYTES, bars + 8 * (B_U + (c < 3 ? c : 3)));
          TSIF(c == 0 || c == 4, 116 + (c >> 2));
        }
      }
      epoch = __shfl_sync(0xffffffffu, epoch, 0);
      if (lane < 8) {
        const int src = (b & ~7) | step_src(hg, lane);
        mbar_wait(bars + 8 * B_ATTN, 0);
        TS(20);
        bool seen = false;
#pragma unroll 1
        for (int spins = 0; spins < SPIN_LIMIT; spins++) {
          const bool now = !seen && (int)(flag_read(g_cnt + C_O + 32 * src) - (epoch + 1)) >= 0;
          if (now && lane >= 1 && lane < 4) bulk_load(sb + off_o(lane), g_O + src * 1280, O_BYTES, bars + 8 * (B_FULL2 + lane));
          seen = seen || now;
          if (__all_sync(0xff, seen)) break;
        }
        TS(21);
        if (lane == 5) bulk_load(sb + OFF_GATE, g_gate + 128 * r, 512, bars + 8 * (B_FULL2 + 5));
#pragma unroll 1
        for (int j = 4; j < 8; j++) {
          if (lane == j) {
            mbar_wait(bars + 8 * (j < 6 ? B_C34 : B_EMPTY2 + j - 6), 0);
            bulk_load(sb + off_o(j), g_O + src * 1280, O_BYTES, bars + 8 * (B_FULL2 + j));
          }
          __syncwarp(0xff);
        }
        TS(22);
      }
    } else if (w == 2) {
      mbar_wait(bars + 8 * B_PREP, 0);
      flag_signal(g_cnt + C_PREP, 16, lane);
      TS(25);
      if (lane == 0) {
        mbar_arrive(bars + 8 * B_USIG);
        mbar_expect_tx(bars + 8 * B_ORB, O_BYTES / 4 + 64);
        mbar_wait(bars + 8 * B_GATE, 0);
        publish(g_gate + 16 * b, sb + OFF_GATE + 64 * hg, 64);
        bulk_load(sb + OFF_GATE + 64 * hg, g_gate + 16 * b, 64, bars + 8 * B_ORB);
        mbar_wait(bars + 8 * B_ATTN, 0);
        publish(g_O + b * 1280, sb + OFF_OA, O_BYTES);
        tma_2d(sb + OFF_KVX + 10240, &m.ol, 48, b * 160, bars + 8 * B_ORB);
        TS(74);
        mbar_wait(bars + 8 * B_ORB, 0);
        flag_bump(g_cnt + C_O + 32 * b);
        TS(26);
      }
    } else {
      if (lane == 0) {
        uint4* dst = g_WO + (hg * 8 + (r >> 1)) * 800 + (r & 1) * 80;
        mbar_wait(bars + 8 * B_S3, 0);
        asm volatile("cp.async.bulk.prefetch.L2.global [%0], 6400;" ::"l"(p.wo + b * 3200) : "memory");
        mbar_wait(bars + 8 * B_P1, 0);
        mbar_wait(bars + 8 * WB_TRIG, 0);
        mbar_expect_tx(bars + 8 * B_WST, WO_BYTES / 2);
        tma_3d(sb + OFF_WA, &m.wo, 0, 40 * r, 5 * hg, bars + 8 * B_WST);
        mbar_wait(bars + 8 * B_WST, 0);
#pragma unroll 1
        for (int n = 0; n < 5; n++) bulk_store(dst + 160 * n, sb + OFF_WA + 1280 * n, 1280);
        bulk_wait_read();
        mbar_expect_tx(bars + 8 * B_WST, WO_BYTES / 2);
#pragma unroll 1
        for (int n = 0; n < 5; n++) bulk_load(sb + OFF_WA + 1280 * n, dst + 160 * n, 1280, bars + 8 * B_WST);
        mbar_wait(bars + 8 * B_WST, 1);
        flag_bump(g_cnt + C_W + 32 * hg);
        mbar_arrive(bars + 8 * B_WOP);
        TS(71);
        mbar_expect_tx(bars + 8 * B_C34, 3 * (U_BYTES / 4));
        mbar_expect_tx(bars + 8 * B_YRB, 2 * (U_BYTES / 4));
#pragma unroll 1
        for (int c = 0; c < 5; c++) {
          mbar_wait(bars + 8 * (B_YST + c), 0);
          publish(g_U + (5 * b + c) * U_PITCH, sb + off_ch(c), U_BYTES);
          tma_2d(sb + off_ch(c), &m.yl, 48, (5 * b + c) * (U_PITCH / 8), bars + 8 * (c < 3 ? B_C34 : B_YRB));
        }
        TS(75);
        mbar_wait(bars + 8 * B_C34, 0);
        mbar_wait(bars + 8 * B_YRB, 0);
        flag_bump(g_cnt + C_Y + 32 * (b >> 4));
        TS(27);
        mbar_expect_tx(bars + 8 * B_YFULL, 20480);
        flag_wait(g_cnt + C_Y + 32 * hg, (lds32(sb + OFF_EPOCH) + 1) * 16);
        TS(24);
        tma_2d(sb + OFF_YT, &m.y, 128 * r, 80 * hg, bars + 8 * B_YFULL);
        tma_2d(sb + OFF_YT + 10240, &m.y, 128 * r + 64, 80 * hg, bars + 8 * B_YFULL);
      }
    }
  } else {
    asm volatile("setmaxnreg.inc.sync.aligned.u32 152;");
    FftConst fc;
    if (wg < 2) {
      float acc[120];
#pragma unroll
      for (int i = 0; i < 120; i++) acc[i] = 0.f;
      const uint32_t da = desc_lo(sb + wg * 8192, 16), db = desc_lo(sb + ST_W, 8192), dc = desc_lo(sb + ST_WT, 2048);
#pragma unroll
      for (int k = 0; k < 4; k++) {
        mbar_wait(bars + 8 * (B_F0 + k), 0);
        TSIF(w == 0 && wg == 0 && k == 0, 1);
        wg_fence();
        WgSST<192>::mma<HI_SW128, HI_SW128>(acc, da + 2 * k, desc_lo(sb + ST_W, 2048) + 384 * k, 1);
        wg_commit();
      }
      mbar_wait(bars + 8 * B_FULL1, 0);
      wg_fence();
#pragma unroll
      for (int k = 0; k < 4; k++) WgSST<48>::mma<HI_SW128, HI_SW32>(acc + 96, da + 2 * k, dc + 32 * k, 1);
      wg_commit();
#pragma unroll 1
      for (int kb = 1; kb < 10; kb++) {
        mbar_wait(bars + 8 * (B_FULL1 + (kb & 3)), (kb >> 2) & 1);
        const uint32_t so = (kb & 3) * (STAGE_BYTES >> 4);
        wg_fence();
#pragma unroll
        for (int k = 0; k < 4; k++) {
          WgSST<192>::mma<HI_SW128, HI_SW128>(acc, da + so + 2 * k, db + so + 128 * k, 1);
          WgSST<48>::mma<HI_SW128, HI_SW32>(acc + 96, da + so + 2 * k, dc + so + 32 * k, 1);
        }
        wg_commit();
        wg_wait<1>();
        if (lane == 0) mbar_arrive(bars + 8 * (kb == 4 ? B_E3 : B_EMPTY1 + ((kb - 1) & 3)));
      }
      mbar_wait(bars + 8 * B_EPOCH, 0);
      const uint32_t tag = lds32(sb + OFF_EPOCH) + 1;
      mbar_wait(bars + 8 * B_S3, 0);
      wg_wait<0>();
      pin<120>(acc);
      if (lane == 0) mbar_arrive(bars + 8 * B_P1);
      TSM(w == 0, 3 + wg);
      attention(acc, sb, b, wg, w, lane, tag, fc);
    } else {
      const int tw = tid & 127, chl = 64 * (b & 1) + 8 * w + (lane >> 2);
      uint4* up = g_U + chl * U_PITCH + ((4 * (b >> 1) + (lane & 3)) ^ ((b >> 2) & 1));
      uint2 sw[10];
      uint32_t dv = 0;
      if (lane < 5) dv = __ldg(reinterpret_cast<const unsigned short*>(p.ssm_D) + 5 * b + lane);
#pragma unroll
      for (int i = 0; i < 10; i++) sw[i] = ldg64(reinterpret_cast<const uint2*>(p.shift_k) + chl + 128 * (i >> 1) + 32 * (i & 1));
      uint32_t tab[12];
      uint32_t tt[2];
      fft_tables(tab, tw);
      fft_twiddles(tt, tw);
      uint4 res[10];
#pragma unroll
      for (int i = 0; i < 10; i++) res[i] = make_uint4(0, 0, 0, 0);
#pragma unroll 1
      for (int slab = 0; slab < 5; slab++) {
#pragma unroll
        for (int i = 0; i < 8; i++) res[i] = res[i + 2];
        prep_slab(res + 8, sw, sb, slab, w, lane);
        TSIF(w == 0, 99 + 4 * slab);
#pragma unroll
        for (int i = 0; i < 8; i++) sw[i] = sw[i + 2];
      }
      TSIF(w == 0, 28);
      __syncwarp();
      if (lane == 0) mbar_arrive(bars + 8 * B_KVD + ((res[8].x ^ res[9].x) & p.zero));
      mbar_wait(bars + 8 * B_KVD, 0);
      fft_tables_store(tab, sb, tw);
      mbar_wait(bars + 8 * B_LAST, 0);
#pragma unroll
      for (int i = 0; i < 10; i++) up[(128 * (i >> 1) + 32 * (i & 1)) * U_PITCH] = res[i];
      __syncwarp();
      if (lane == 0) mbar_arrive(bars + 8 * B_PREP);
      TSIF(w == 0, 5);
      if (!G_IN) {
        mbar_wait(bars + 8 * B_LAST, 0);
        prep_gate(p, sb, b, w, lane);
        __syncwarp();
        if (lane == 0) mbar_arrive(bars + 8 * B_GATE);
        TSIF(w == 0, 72);
      }
      mbar_wait(bars + 8 * B_HB, 0);
      TSIF(w == 0, 2);
      const uint32_t ha = sb + U_BYTES + ((tw >> 3) * 16 + 8 + (tw & 7)) * 16;
      uint4 hv[5];
#pragma unroll
      for (int c = 0; c < 5; c++) hv[c] = lds128(ha + off_ch(c));
      __syncwarp();
#pragma unroll
      for (int c = 0; c < 5; c++) sts128((ha ^ 16) + off_ch(c), hv[c].x, hv[c].y, hv[c].z, hv[c].w);
      asm volatile("st.shared.v2.u32 [%0], {%1, %2};" ::"r"(sb + OFF_TT + 8 * tw), "r"(tt[0]), "r"(tt[1]) : "memory");
      if (tw < 5) asm volatile("st.shared.f32 [%0], %1;" ::"r"(sb + OFF_D + 4 * tw), "f"(bf_lo(dv) * 0.125f) : "memory");
      fence_async_smem();
      __syncwarp();
      if (lane == 0) mbar_arrive(bars + 8 * B_HA);
      TSIF(w == 0, 6);
      mbar_wait(bars + 8 * B_HA, 0);
      fft_matrices(fc, sb, w, lane);
    }

    TSM(w == 0 && wg == 2, 124);
#pragma unroll 1
    for (uint32_t tasks = wg == 0 ? TASK0 : wg == 1 ? TASK1 : TASK2; tasks; tasks >>= 4) {
      const int c = (tasks & 7) - 1;
      conv_channel(fc, p, b, sb, c, wg, w, lane);
      if (lane == 0) mbar_arrive(bars + 8 * (B_YST + c));
      TSM(w == 0, 10 + c);
    }

    if (wg != 1) {
      const int wg = warp >> 3;
      const int g = lane >> 2;
      float acc[40];
#pragma unroll
      for (int i = 0; i < 40; i++) acc[i] = 0.f;
      const uint32_t da = desc_lo(sb + wg * 1024, 2048), db = desc_lo(sb, 2560);
      mbar_wait(bars + 8 * B_ORB, 0);
      mbar_wait(bars + 8 * B_FULL2, 0);
      TSM(w == 0, 15 + wg);
#pragma unroll 1
      for (int j = 0; j < 8; j++) {
        if (j == 1 - wg) mbar_wait(bars + 8 * B_CVD, 0);
        mbar_wait(bars + 8 * (B_FULL2 + j), 0);
        TSM(w == 0 && wg == 0, 44 + (j < 4 ? j : j + 6));
        const uint32_t oa = da + (off_o(j) >> 4), ob = db + (off_w(j) >> 4);
        wg_fence();
#pragma unroll
        for (int k = 0; k < 5; k++) WgSST<80>::mma<HI_NONE, HI_SW32>(acc, oa + 256 * k, ob + 32 * k, 1);
        wg_commit();
        wg_wait<1>();
        if (j >= 1 && j <= 4 && lane == 0) mbar_arrive(bars + 8 * (B_EMPTY2 + j - 1));
      }
      TSIF(w == 0 && wg == 0, 113);
      const int tr = 64 * wg + 16 * w + (lane & 15);
      const uint32_t fm = sb + OFF_QS + tr * 128, fx = (lane >> 4) ^ (tr & 7);
      const uint32_t ft = sb + OFF_QT + tr * 32 + (((lane >> 4) ^ (tr >> 2)) & 1) * 16;
      const float g0 = __uint_as_float(lds32(sb + OFF_GATE + (64 * wg + 16 * w + g) * 4));
      const float g1 = __uint_as_float(lds32(sb + OFF_GATE + (64 * wg + 16 * w + 8 + g) * 4));
      const uint32_t ga = pack2(g0, g0), gb = pack2(g1, g1);
      const uint32_t na = pack2(1.f - g0, 1.f - g0), nb = pack2(1.f - g1, 1.f - g1);

      uint32_t qf[20];
      mbar_wait(bars + 8 * B_QF, 0);
      TSM(w == 0 && wg == 0, 99);
#pragma unroll
      for (int j = 0; j < 5; j++) ldsm4(qf + 4 * j, j < 4 ? fm + ((fx ^ (2 * j)) << 4) : ft);
#pragma unroll
      for (int i = 0; i < 20; i++) {
        qf[i] = bmul((i & 1) ? gb : ga, qf[i]);
        asm volatile("" : "+r"(qf[i]));
      }

      wg_wait<0>();
      pin<40>(acc);
      TSM(w == 0, 17 + wg);
      uint32_t pb[20];
#pragma unroll
      for (int j = 0; j < 10; j++) {
        pb[2 * j] = bmul(na, pack2(acc[4 * j], acc[4 * j + 1]));
        pb[2 * j + 1] = bmul(nb, pack2(acc[4 * j + 2], acc[4 * j + 3]));
        asm volatile("" : "+r"(pb[2 * j]), "+r"(pb[2 * j + 1]));
      }
      const uint32_t ya = sb + OFF_YT + wg * 10240 + ((lane >> 4) * 8 + (lane & 7)) * 128 +
                          (((2 * w + (((lane >> 3) & 1) ^ wg)) ^ (lane & 7)) << 4);
      mbar_wait(bars + 8 * B_YFULL, 0);
      TSM(w == 0 && wg == 0, 19);
#pragma unroll
      for (int j = 0; j < 5; j++) {
        uint32_t y[4];
        ldsm4t(y, ya + 2048 * j);
#pragma unroll
        for (int i = 0; i < 4; i++)
          qf[4 * j + i] = bfma(qf[4 * j + i], y[i], pb[4 * j + i]);
      }
#pragma unroll
      for (int j = 0; j < 5; j++) stsm4(j < 4 ? fm + ((fx ^ (2 * j)) << 4) : ft, qf + 4 * j);
      fence_async_smem();
      __syncwarp();
      if (lane == 0) {
        const int row = 64 * wg + 16 * w;
        asm volatile("cp.async.bulk.tensor.2d.global.shared::cta.bulk_group [%0, {%2, %3}], [%1];"
                     ::"l"(&m.om), "r"(sb + OFF_QS + row * 128), "r"(80 * hg), "r"(128 * r + row) : "memory");
        asm volatile("cp.async.bulk.tensor.2d.global.shared::cta.bulk_group [%0, {%2, %3}], [%1];"
                     ::"l"(&m.ot), "r"(sb + OFF_QT + row * 32), "r"(80 * hg + 64), "r"(128 * r + row) : "memory");
        asm volatile("cp.async.bulk.commit_group;\ncp.async.bulk.wait_group.read 0;" ::: "memory");
      }
      TSM(w == 0 || w == 3, 40 + 2 * wg + (w & 1));
    }
  }
}

typedef CUresult (*EncodeFn)(CUtensorMap*, CUtensorMapDataType, cuuint32_t, void*, const cuuint64_t*, const cuuint64_t*,
                             const cuuint32_t*, const cuuint32_t*, CUtensorMapInterleave, CUtensorMapSwizzle,
                             CUtensorMapL2promotion, CUtensorMapFloatOOBfill);

void encode(EncodeFn fn, CUtensorMap* tm, const void* base, int rank, const cuuint64_t* dims, const cuuint64_t* strides,
            const cuuint32_t* box, CUtensorMapSwizzle swz) {
  const cuuint32_t ones[3] = {1, 1, 1};
  fn(tm, CU_TENSOR_MAP_DATA_TYPE_BFLOAT16, rank, const_cast<void*>(base), dims, strides, box, ones,
     CU_TENSOR_MAP_INTERLEAVE_NONE, swz, CU_TENSOR_MAP_L2_PROMOTION_L2_128B, CU_TENSOR_MAP_FLOAT_OOB_FILL_NONE);
}

}

extern "C" void kernel_launch(void* const* d_in, const int* in_sizes, int n_in, void* d_out, int out_size) {
  (void)in_sizes; (void)n_in; (void)out_size;
  Params p;
  p.q = (const __nv_bfloat16*)d_in[0];
  p.k = (const __nv_bfloat16*)d_in[1];
  p.v = (const __nv_bfloat16*)d_in[2];
  p.shift_k = (const __nv_bfloat16*)d_in[3];
  p.ssm_k = (const __nv_bfloat16*)d_in[4];
  p.ssm_D = (const __nv_bfloat16*)d_in[5];
  p.wqkv = (const __nv_bfloat16*)d_in[7];
  p.wo = (const __nv_bfloat16*)d_in[8];
  p.gate_w = (const __nv_bfloat16*)d_in[9];
  p.out = (__nv_bfloat16*)d_out;
  p.zero = 0;

  static EncodeFn fn = nullptr;
  static void *yaddr = nullptr, *oaddr = nullptr;
  if (!fn) {
    cudaDriverEntryPointQueryResult qr;
    void* f = nullptr;
    cudaGetDriverEntryPoint("cuTensorMapEncodeTiled", &f, cudaEnableDefault, &qr);
    fn = (EncodeFn)f;
    cudaGetSymbolAddress(&yaddr, g_U);
    cudaGetSymbolAddress(&oaddr, g_O);
    cudaFuncSetAttribute(fused_kernel, cudaFuncAttributeMaxDynamicSharedMemorySize, SMEM_BYTES);
  }
  Maps m;
  {
    const cuuint64_t dims[3] = {640, 1024, 2}, st[2] = {2560, 1280};
    const cuuint32_t box[3] = {64, 64, 2};
    encode(fn, &m.x, p.q, 3, dims, st, box, CU_TENSOR_MAP_SWIZZLE_128B);
  }
  {
    const cuuint64_t dims[3] = {640, 640, 3}, st[2] = {3840, 1280};
    const cuuint32_t box[3] = {64, 64, 3}, boxt[3] = {16, 64, 3};
    encode(fn, &m.wm, p.wqkv, 3, dims, st, box, CU_TENSOR_MAP_SWIZZLE_128B);
    encode(fn, &m.wt, p.wqkv, 3, dims, st, boxt, CU_TENSOR_MAP_SWIZZLE_32B);
    const cuuint32_t boxh[3] = {64, 16, 3};
    encode(fn, &m.wh, p.wqkv, 3, dims, st, boxh, CU_TENSOR_MAP_SWIZZLE_128B);
  }
  {
    const cuuint64_t dims[3] = {64, 2048, 10}, st[2] = {1280, 128};
    const cuuint32_t boxk[3] = {64, 35, 1}, boxv[3] = {64, 32, 1};
    encode(fn, &m.k, p.k, 3, dims, st, boxk, CU_TENSOR_MAP_SWIZZLE_128B);
    encode(fn, &m.v, p.v, 3, dims, st, boxv, CU_TENSOR_MAP_SWIZZLE_128B);
  }
  {
    const cuuint64_t dims[3] = {16, 640, 40}, st[2] = {1280, 32};
    const cuuint32_t box[3] = {16, 40, 5};
    encode(fn, &m.wo, p.wo, 3, dims, st, box, CU_TENSOR_MAP_SWIZZLE_32B);
  }
  {
    const cuuint64_t dims[2] = {2048, 640}, st[1] = {U_PITCH * 16};
    const cuuint32_t box[2] = {64, 80};
    encode(fn, &m.y, yaddr, 2, dims, st, box, CU_TENSOR_MAP_SWIZZLE_128B);
    const cuuint64_t dl[2] = {64, DIM * U_PITCH / 8}, dol[2] = {64, NCTA * 160}, sl[1] = {128};
    const cuuint32_t bl[2] = {16, 32}, bol[2] = {16, 160};
    encode(fn, &m.yl, yaddr, 2, dl, sl, bl, CU_TENSOR_MAP_SWIZZLE_NONE);
    encode(fn, &m.ol, oaddr, 2, dol, sl, bol, CU_TENSOR_MAP_SWIZZLE_NONE);
  }
  {
    const cuuint64_t dims[2] = {640, 2048}, st[1] = {1280};
    const cuuint32_t bqm[2] = {64, 128}, bqt[2] = {16, 128}, bom[2] = {64, 16}, bot[2] = {16, 16};
    encode(fn, &m.qm, p.q, 2, dims, st, bqm, CU_TENSOR_MAP_SWIZZLE_128B);
    encode(fn, &m.qt, p.q, 2, dims, st, bqt, CU_TENSOR_MAP_SWIZZLE_32B);
    encode(fn, &m.om, p.out, 2, dims, st, bom, CU_TENSOR_MAP_SWIZZLE_128B);
    encode(fn, &m.ot, p.out, 2, dims, st, bot, CU_TENSOR_MAP_SWIZZLE_32B);
  }
  fused_kernel<<<NCTA, NTHR, SMEM_BYTES>>>(m, p);
}
```

```cpp
#include <cuda.h>
#include <cuda_bf16.h>
#include <cuda_runtime.h>
#include <stdint.h>

namespace {

constexpr int SEQ = 2048, DIM = 640, NCTA = 128, NTHR = 512;

#define KV_KB 2
#define DEV_EXIT 0
#define FENCE_LO 0
#define FENCE_HI 0
#define WB_TRIG B_USIG
#define T_ISSUE 288
#define U_RB 1
#define T_INIT 448
#define TASK0 0x3
#define TASK1 0x52
#define TASK2 0x41

constexpr uint32_t STAGE_BYTES = 47104, ST_W = 16384, ST_WT = 40960;
constexpr uint32_t O_BYTES = 20480, WO_BYTES = 12800;
constexpr uint32_t OFF_OA = 0;
constexpr uint32_t OFF_QS = 3 * O_BYTES, OFF_QT = OFF_QS + 16384;
constexpr uint32_t OFF_WC = 81920;
constexpr uint32_t OFF_WA = 94720;
constexpr uint32_t OFF_GATE = 145920;
constexpr uint32_t OFF_TT = 146432;
constexpr uint32_t OFF_KVX = 148480;
constexpr uint32_t OFF_CH3 = 163840;
constexpr uint32_t CH_BYTES = 12288, U_BYTES = 4096;
constexpr uint32_t OFF_FT = 225280, OFF_GT = 229376;
constexpr uint32_t OFF_CH0 = 188416;
constexpr uint32_t OFF_KVS = OFF_CH0, KVS_V = 4480, KVS_BYTES = 8576;
constexpr uint32_t OFF_YT = 163840;
constexpr uint32_t OFF_BAR = 231936;
constexpr uint32_t SMEM_BYTES = OFF_BAR + 512;

enum : uint32_t {
  B_EMPTY1 = 0, B_S3 = 3, B_E3 = 4, B_EMPTY2 = 5, B_ATTN = 9, B_P1 = 10,
  B_GATE = 11, B_HA = 12, B_KVD = 13, B_PREP = 14, B_YST = 15,
  B_CVD = 20,
  B_FULL2 = 21, B_U = 29, B_KV = 33, B_HB = 38, B_C34 = 39, B_YRB = 40, B_YFULL = 41, B_EPOCH = 42, B_LAST = 43,
  B_WOP = 44, B_USIG = 45, B_WST = 46, B_QF = 47, B_ORB = 48, B_URB = 49,
  B_F0 = 50, B_FULL1 = 54
};
constexpr uint32_t OFF_EPOCH = OFF_BAR + 8 * 58, OFF_D = OFF_BAR + 8 * 60;
__device__ __forceinline__ uint32_t off_o(int j) { return j < 4 ? OFF_OA + j * O_BYTES : j < 6 ? OFF_CH0 + (j - 4) * O_BYTES : OFF_OA + (j - 6) * O_BYTES; }
__device__ __forceinline__ uint32_t off_w(int j) { return j < 4 ? OFF_WA + j * WO_BYTES : j == 4 ? OFF_KVX : j == 5 ? OFF_WC : OFF_WA + (j - 6) * WO_BYTES; }
__device__ __forceinline__ int step_src(int hg, int j) { return j == 0 ? hg : j <= hg ? j - 1 : j; }
__device__ __forceinline__ bool tail_first(int hg) { return (hg & 3) == 3; }
__device__ __forceinline__ uint32_t off_ch(int c) { return (c < 3 ? OFF_CH0 : OFF_CH3 - 3 * CH_BYTES) + c * CH_BYTES; }

#define U_PITCH 264
__device__ __align__(1024) uint4 g_U[DIM * U_PITCH];
__device__ __align__(128) uint4 g_O[NCTA * 1280];
__device__ uint4 g_WO[64 * 800];
__device__ uint4 g_halo[NCTA * 2 * 7 * 32];
__device__ __align__(128) float g_gate[SEQ];
__device__ unsigned g_cnt[32 * (1 + 2 * 16 + 8 + NCTA)];
constexpr int C_LAUNCH = 0, C_PREP = 32, C_Y = 32 * 17, C_W = 32 * 33, C_O = 32 * 41;

#define TSM(cond, slot) do { } while (0)
#define TSIF(cond, slot) do { if (__LINE__ >= FENCE_LO && __LINE__ < FENCE_HI) sched_fence(); } while (0)
__device__ __forceinline__ void sched_fence() {
  asm volatile("{\n.reg .pred p;\n.reg .u32 c;\nmov.u32 c, %%clock;\nsetp.eq.u32 p, c, 0;\n@p st.shared.u32 [%0], c;\n}"
               ::"r"(1024 + OFF_EPOCH + 4) : "memory");
}
#define TS(slot) TSIF(true, slot)

struct Params {
  const __nv_bfloat16 *q, *k, *v, *shift_k, *ssm_k, *ssm_D, *wqkv, *wo, *gate_w;
  __nv_bfloat16* out;
  uint32_t zero;
};

constexpr int SPIN_LIMIT = 1 << 17;

__device__ __forceinline__ void mbar_init(uint32_t bar, uint32_t count) {
  asm volatile("mbarrier.init.shared::cta.b64 [%0], %1;" ::"r"(bar), "r"(count) : "memory");
}
__device__ __forceinline__ void mbar_expect_tx(uint32_t bar, uint32_t bytes) {
  asm volatile("mbarrier.arrive.expect_tx.shared::cta.b64 _, [%0], %1;" ::"r"(bar), "r"(bytes) : "memory");
}
__device__ __forceinline__ void mbar_arrive(uint32_t bar) {
  asm volatile("mbarrier.arrive.shared::cta.b64 _, [%0];" ::"r"(bar) : "memory");
}
__device__ __forceinline__ void mbar_wait(uint32_t bar, uint32_t parity) {
  uint32_t ok;
  int spins = 0;
  do {
      asm volatile("{\n.reg .pred p;\nmbarrier.try_wait.parity.shared::cta.b64 p, [%1], %2;\nselp.b32 %0, 1, 0, p;\n}"
                   : "=r"(ok) : "r"(bar), "r"(parity) : "memory");
    if (++spins > SPIN_LIMIT) break;
  } while (!ok);
}
__device__ __forceinline__ unsigned flag_read(const unsigned* p) {
  unsigned v;
  asm volatile("ld.relaxed.gpu.global.u32 %0, [%1];" : "=r"(v) : "l"(p) : "memory");
  return v;
}
__device__ __forceinline__ void flag_poll(const unsigned* p, unsigned target) {
  unsigned v;
  int spins = 0;
  do {
    asm volatile("ld.relaxed.gpu.global.u32 %0, [%1];" : "=r"(v) : "l"(p) : "memory");
    if (++spins > SPIN_LIMIT) break;
  } while ((int)(v - target) < 0);
}
__device__ __forceinline__ void flag_wait(const unsigned* p, unsigned target) {
  flag_poll(p, target);
}
__device__ __forceinline__ void flag_signal(unsigned* p, int n, int lane) {
  if (lane == 0) asm volatile("fence.release.gpu;" ::: "memory");
  __syncwarp();
  if (lane < n) asm volatile("red.relaxed.gpu.global.add.u32 [%0], 1;" ::"l"(p + 32 * lane) : "memory");
}
__device__ __forceinline__ void flag_bump(unsigned* p) {
  asm volatile("red.relaxed.gpu.global.add.u32 [%0], 1;" ::"l"(p) : "memory");
}
__device__ __forceinline__ void fence_async_smem() { asm volatile("fence.proxy.async.shared::cta;" ::: "memory"); }
__device__ __forceinline__ void wg_sync(int id) { asm volatile("bar.sync %0, 128;" ::"r"(id) : "memory"); }

__device__ __forceinline__ void tma_2d(uint32_t dst, const CUtensorMap* tm, int c0, int c1, uint32_t bar) {
  asm volatile("cp.async.bulk.tensor.2d.shared::cluster.global.mbarrier::complete_tx::bytes [%0], [%1, {%3, %4}], [%2];"
               ::"r"(dst), "l"(tm), "r"(bar), "r"(c0), "r"(c1) : "memory");
}
__device__ __forceinline__ void tma_3d(uint32_t dst, const CUtensorMap* tm, int c0, int c1, int c2, uint32_t bar) {
  asm volatile("cp.async.bulk.tensor.3d.shared::cluster.global.mbarrier::complete_tx::bytes [%0], [%1, {%3, %4, %5}], [%2];"
               ::"r"(dst), "l"(tm), "r"(bar), "r"(c0), "r"(c1), "r"(c2) : "memory");
}
__device__ __forceinline__ void bulk_load(uint32_t dst, const void* src, uint32_t bytes, uint32_t bar) {
  asm volatile("cp.async.bulk.shared::cluster.global.mbarrier::complete_tx::bytes [%0], [%1], %2, [%3];"
               ::"r"(dst), "l"(src), "r"(bytes), "r"(bar) : "memory");
}
__device__ __forceinline__ void bulk_store(void* dst, uint32_t src, uint32_t bytes) {
  asm volatile("cp.async.bulk.global.shared::cta.bulk_group [%0], [%1], %2;" ::"l"(dst), "r"(src), "r"(bytes) : "memory");
}
__device__ __forceinline__ void bulk_wait_read() {
  asm volatile("cp.async.bulk.commit_group;\ncp.async.bulk.wait_group.read 0;" ::: "memory");
}

__device__ __forceinline__ void publish(void* dst, uint32_t src, uint32_t bytes) {
  bulk_store(dst, src, bytes);
  bulk_wait_read();
}

__device__ __forceinline__ void wg_fence() { asm volatile("wgmma.fence.sync.aligned;" ::: "memory"); }
__device__ __forceinline__ void wg_commit() { asm volatile("wgmma.commit_group.sync.aligned;" ::: "memory"); }
template <int N> __device__ __forceinline__ void wg_wait() { asm volatile("wgmma.wait_group.sync.aligned %0;" ::"n"(N) : "memory"); }
__device__ __forceinline__ uint32_t desc_lo(uint32_t addr, uint32_t lbo) { return ((addr & 0x3FFFF) >> 4) | ((lbo >> 4) << 16); }
constexpr uint32_t desc_hi(uint32_t sbo, uint32_t swz) { return (sbo >> 4) | (swz << 30); }
constexpr uint32_t HI_SW128 = desc_hi(1024, 1), HI_SW64 = desc_hi(512, 2), HI_SW32 = desc_hi(256, 3), HI_NONE = desc_hi(128, 0);
template <int N> __device__ __forceinline__ void pin(float* d) {
#pragma unroll
  for (int i = 0; i < N; i++) asm volatile("" : "+f"(d[i])::"memory");
}

__device__ __forceinline__ uint32_t lds32(uint32_t a) {
  uint32_t v;
  asm volatile("ld.volatile.shared.u32 %0, [%1];" : "=r"(v) : "r"(a) : "memory");
  return v;
}
__device__ __forceinline__ uint2 ldg64(const void* a) {
  uint2 v;
  asm volatile("ld.global.nc.v2.u32 {%0, %1}, [%2];" : "=r"(v.x), "=r"(v.y) : "l"(a) : "memory");
  return v;
}
__device__ __forceinline__ void ldsm4(uint32_t* r, uint32_t a) {
  asm volatile("ldmatrix.sync.aligned.m8n8.x4.shared.b16 {%0, %1, %2, %3}, [%4];"
               : "=r"(r[0]), "=r"(r[1]), "=r"(r[2]), "=r"(r[3]) : "r"(a) : "memory");
}
__device__ __forceinline__ void ldsm4t(uint32_t* r, uint32_t a) {
  asm volatile("ldmatrix.sync.aligned.m8n8.x4.trans.shared.b16 {%0, %1, %2, %3}, [%4];"
               : "=r"(r[0]), "=r"(r[1]), "=r"(r[2]), "=r"(r[3]) : "r"(a) : "memory");
}
__device__ __forceinline__ uint2 lds64(uint32_t a) {
  uint2 v;
  asm volatile("ld.shared.v2.u32 {%0, %1}, [%2];" : "=r"(v.x), "=r"(v.y) : "r"(a) : "memory");
  return v;
}
__device__ __forceinline__ uint4 lds128(uint32_t a) {
  uint4 v;
  asm volatile("ld.shared.v4.u32 {%0, %1, %2, %3}, [%4];" : "=r"(v.x), "=r"(v.y), "=r"(v.z), "=r"(v.w) : "r"(a) : "memory");
  return v;
}
__device__ __forceinline__ void sts128(uint32_t a, uint32_t x, uint32_t y, uint32_t z, uint32_t w) {
  asm volatile("st.shared.v4.u32 [%0], {%1, %2, %3, %4};" ::"r"(a), "r"(x), "r"(y), "r"(z), "r"(w) : "memory");
}
__device__ __forceinline__ void stsm4(uint32_t a, const uint32_t* r) {
  asm volatile("stmatrix.sync.aligned.m8n8.x4.shared.b16 [%0], {%1, %2, %3, %4};" ::"r"(a), "r"(r[0]), "r"(r[1]), "r"(r[2]), "r"(r[3]) : "memory");
}
__device__ __forceinline__ uint32_t pack2(float lo, float hi) {
  uint32_t r;
  asm("cvt.rn.bf16x2.f32 %0, %1, %2;" : "=r"(r) : "f"(hi), "f"(lo));
  return r;
}
__device__ __forceinline__ uint32_t movm(uint32_t a) {
  uint32_t d;
  asm volatile("movmatrix.sync.aligned.m8n8.trans.b16 %0, %1;" : "=r"(d) : "r"(a));
  return d;
}
__device__ __forceinline__ uint32_t bmul(uint32_t a, uint32_t b) {
  uint32_t d;
  asm("mul.rn.bf16x2 %0, %1, %2;" : "=r"(d) : "r"(a), "r"(b));
  return d;
}
__device__ __forceinline__ uint32_t badd(uint32_t a, uint32_t b) {
  uint32_t d;
  asm("add.rn.bf16x2 %0, %1, %2;" : "=r"(d) : "r"(a), "r"(b));
  return d;
}
__device__ __forceinline__ uint32_t bfma(uint32_t a, uint32_t b, uint32_t c) {
  uint32_t d;
  asm("fma.rn.bf16x2 %0, %1, %2, %3;" : "=r"(d) : "r"(a), "r"(b), "r"(c));
  return d;
}
__device__ __forceinline__ float bf_lo(uint32_t x) { return __uint_as_float(x << 16); }
__device__ __forceinline__ float bf_hi(uint32_t x) { return __uint_as_float(x & 0xFFFF0000u); }
__device__ __forceinline__ float ex2(float x) {
  float y;
  asm("ex2.approx.ftz.f32 %0, %1;" : "=f"(y) : "f"(x));
  return y;
}
__device__ __forceinline__ float rcp(float x) {
  float y;
  asm("rcp.approx.ftz.f32 %0, %1;" : "=f"(y) : "f"(x));
  return y;
}
__device__ __forceinline__ void mma16816(float* d, uint32_t a0, uint32_t a1, uint32_t a2, uint32_t a3, uint32_t b0, uint32_t b1) {
  asm volatile("mma.sync.aligned.m16n8k16.row.col.f32.bf16.bf16.f32 {%0, %1, %2, %3}, {%4, %5, %6, %7}, {%8, %9}, {%0, %1, %2, %3};"
               : "+f"(d[0]), "+f"(d[1]), "+f"(d[2]), "+f"(d[3])
               : "r"(a0), "r"(a1), "r"(a2), "r"(a3), "r"(b0), "r"(b1));
}
__device__ __forceinline__ void mma1688(float* d, uint32_t a0, uint32_t a1, uint32_t b0) {
  asm volatile("mma.sync.aligned.m16n8k8.row.col.f32.bf16.bf16.f32 {%0, %1, %2, %3}, {%4, %5}, {%6}, {%0, %1, %2, %3};"
               : "+f"(d[0]), "+f"(d[1]), "+f"(d[2]), "+f"(d[3])
               : "r"(a0), "r"(a1), "r"(b0));
}

template <int N> struct WgRS;
template <int N> struct WgSST;
template <> struct WgRS<32> {
  template <uint32_t HB>
  static __device__ __forceinline__ void mma(float* d, const uint32_t* a, uint32_t db) {
    asm volatile("{\n.reg .pred p;\n.reg .b64 db;\nsetp.ne.b32 p, %22, 0;\n"
      "mov.b64 db, {%20, %21};\n"
      "wgmma.mma_async.sync.aligned.m64n32k16.f32.bf16.bf16 {"
      "%0, %1, %2, %3, %4, %5, %6, %7, %8, %9, %10, %11, %12, %13, %14, %15"
      "}, {%16, %17, %18, %19}, db, p, 1, 1, 1;\n}\n"
      : "+f"(d[0]), "+f"(d[1]), "+f"(d[2]), "+f"(d[3]), "+f"(d[4]), "+f"(d[5]), "+f"(d[6]), "+f"(d[7]),
        "+f"(d[8]), "+f"(d[9]), "+f"(d[10]), "+f"(d[11]), "+f"(d[12]), "+f"(d[13]), "+f"(d[14]), "+f"(d[15])
      : "r"(a[0]), "r"(a[1]), "r"(a[2]), "r"(a[3]), "r"(db), "n"(HB), "n"(1));
  }
  template <uint32_t HB>
  static __device__ __forceinline__ void set(float* d, const uint32_t* a, uint32_t db) {
    asm volatile("{\n.reg .pred p;\n.reg .b64 db;\nsetp.ne.b32 p, %22, 0;\n"
      "mov.b64 db, {%20, %21};\n"
      "wgmma.mma_async.sync.aligned.m64n32k16.f32.bf16.bf16 {"
      "%0, %1, %2, %3, %4, %5, %6, %7, %8, %9, %10, %11, %12, %13, %14, %15"
      "}, {%16, %17, %18, %19}, db, p, 1, 1, 1;\n}\n"
      : "=f"(d[0]), "=f"(d[1]), "=f"(d[2]), "=f"(d[3]), "=f"(d[4]), "=f"(d[5]), "=f"(d[6]), "=f"(d[7]),
        "=f"(d[8]), "=f"(d[9]), "=f"(d[10]), "=f"(d[11]), "=f"(d[12]), "=f"(d[13]), "=f"(d[14]), "=f"(d[15])
      : "r"(a[0]), "r"(a[1]), "r"(a[2]), "r"(a[3]), "r"(db), "n"(HB), "n"(0));
  }
};
template <> struct WgRS<64> {
  template <uint32_t HB>
  static __device__ __forceinline__ void mma(float* d, const uint32_t* a, uint32_t db) {
    asm volatile("{\n.reg .pred p;\n.reg .b64 db;\nsetp.ne.b32 p, %38, 0;\n"
      "mov.b64 db, {%36, %37};\n"
      "wgmma.mma_async.sync.aligned.m64n64k16.f32.bf16.bf16 {"
      "%0, %1, %2, %3, %4, %5, %6, %7, %8, %9, %10, %11, %12, %13, %14, %15, "
      "%16, %17, %18, %19, %20, %21, %22, %23, %24, %25, %26, %27, %28, %29, %30, %31"
      "}, {%32, %33, %34, %35}, db, p, 1, 1, 1;\n}\n"
      : "+f"(d[0]), "+f"(d[1]), "+f"(d[2]), "+f"(d[3]), "+f"(d[4]), "+f"(d[5]), "+f"(d[6]), "+f"(d[7]),
        "+f"(d[8]), "+f"(d[9]), "+f"(d[10]), "+f"(d[11]), "+f"(d[12]), "+f"(d[13]), "+f"(d[14]), "+f"(d[15]),
        "+f"(d[16]), "+f"(d[17]), "+f"(d[18]), "+f"(d[19]), "+f"(d[20]), "+f"(d[21]), "+f"(d[22]), "+f"(d[23]),
        "+f"(d[24]), "+f"(d[25]), "+f"(d[26]), "+f"(d[27]), "+f"(d[28]), "+f"(d[29]), "+f"(d[30]), "+f"(d[31])
      : "r"(a[0]), "r"(a[1]), "r"(a[2]), "r"(a[3]), "r"(db), "n"(HB), "n"(1));
  }
  template <uint32_t HB>
  static __device__ __forceinline__ void set(float* d, const uint32_t* a, uint32_t db) {
    asm volatile("{\n.reg .pred p;\n.reg .b64 db;\nsetp.ne.b32 p, %38, 0;\n"
      "mov.b64 db, {%36, %37};\n"
      "wgmma.mma_async.sync.aligned.m64n64k16.f32.bf16.bf16 {"
      "%0, %1, %2, %3, %4, %5, %6, %7, %8, %9, %10, %11, %12, %13, %14, %15, "
      "%16, %17, %18, %19, %20, %21, %22, %23, %24, %25, %26, %27, %28, %29, %30, %31"
      "}, {%32, %33, %34, %35}, db, p, 1, 1, 1;\n}\n"
      : "=f"(d[0]), "=f"(d[1]), "=f"(d[2]), "=f"(d[3]), "=f"(d[4]), "=f"(d[5]), "=f"(d[6]), "=f"(d[7]),
        "=f"(d[8]), "=f"(d[9]), "=f"(d[10]), "=f"(d[11]), "=f"(d[12]), "=f"(d[13]), "=f"(d[14]), "=f"(d[15]),
        "=f"(d[16]), "=f"(d[17]), "=f"(d[18]), "=f"(d[19]), "=f"(d[20]), "=f"(d[21]), "=f"(d[22]), "=f"(d[23]),
        "=f"(d[24]), "=f"(d[25]), "=f"(d[26]), "=f"(d[27]), "=f"(d[28]), "=f"(d[29]), "=f"(d[30]), "=f"(d[31])
      : "r"(a[0]), "r"(a[1]), "r"(a[2]), "r"(a[3]), "r"(db), "n"(HB), "n"(0));
  }
};
template <> struct WgSST<48> {
  template <uint32_t HA, uint32_t HB>
  static __device__ __forceinline__ void mma(float* d, uint32_t da, uint32_t db, int sc) {
    asm volatile("{\n.reg .pred p;\n.reg .b64 da, db;\nsetp.ne.b32 p, %28, 0;\n"
      "mov.b64 da, {%24, %25};\nmov.b64 db, {%26, %27};\n"
      "wgmma.mma_async.sync.aligned.m64n48k16.f32.bf16.bf16 {"
      "%0, %1, %2, %3, %4, %5, %6, %7, %8, %9, %10, %11, %12, %13, %14, %15, "
      "%16, %17, %18, %19, %20, %21, %22, %23"
      "}, da, db, p, 1, 1, 0, 1;\n}\n"
      : "+f"(d[0]), "+f"(d[1]), "+f"(d[2]), "+f"(d[3]), "+f"(d[4]), "+f"(d[5]), "+f"(d[6]), "+f"(d[7]),
        "+f"(d[8]), "+f"(d[9]), "+f"(d[10]), "+f"(d[11]), "+f"(d[12]), "+f"(d[13]), "+f"(d[14]), "+f"(d[15]),
        "+f"(d[16]), "+f"(d[17]), "+f"(d[18]), "+f"(d[19]), "+f"(d[20]), "+f"(d[21]), "+f"(d[22]), "+f"(d[23])
      : "r"(da), "n"(HA), "r"(db), "n"(HB), "r"(sc));
  }
};
template <> struct WgSST<80> {
  template <uint32_t HA, uint32_t HB>
  static __device__ __forceinline__ void mma(float* d, uint32_t da, uint32_t db, int sc) {
    asm volatile("{\n.reg .pred p;\n.reg .b64 da, db;\nsetp.ne.b32 p, %44, 0;\n"
      "mov.b64 da, {%40, %41};\nmov.b64 db, {%42, %43};\n"
      "wgmma.mma_async.sync.aligned.m64n80k16.f32.bf16.bf16 {"
      "%0, %1, %2, %3, %4, %5, %6, %7, %8, %9, %10, %11, %12, %13, %14, %15, "
      "%16, %17, %18, %19, %20, %21, %22, %23, %24, %25, %26, %27, %28, %29, %30, %31, "
      "%32, %33, %34, %35, %36, %37, %38, %39"
      "}, da, db, p, 1, 1, 0, 1;\n}\n"
      : "+f"(d[0]), "+f"(d[1]), "+f"(d[2]), "+f"(d[3]), "+f"(d[4]), "+f"(d[5]), "+f"(d[6]), "+f"(d[7]),
        "+f"(d[8]), "+f"(d[9]), "+f"(d[10]), "+f"(d[11]), "+f"(d[12]), "+f"(d[13]), "+f"(d[14]), "+f"(d[15]),
        "+f"(d[16]), "+f"(d[17]), "+f"(d[18]), "+f"(d[19]), "+f"(d[20]), "+f"(d[21]), "+f"(d[22]), "+f"(d[23]),
        "+f"(d[24]), "+f"(d[25]), "+f"(d[26]), "+f"(d[27]), "+f"(d[28]), "+f"(d[29]), "+f"(d[30]), "+f"(d[31]),
        "+f"(d[32]), "+f"(d[33]), "+f"(d[34]), "+f"(d[35]), "+f"(d[36]), "+f"(d[37]), "+f"(d[38]), "+f"(d[39])
      : "r"(da), "n"(HA), "r"(db), "n"(HB), "r"(sc));
  }
};
template <> struct WgSST<192> {
  template <uint32_t HA, uint32_t HB>
  static __device__ __forceinline__ void mma(float* d, uint32_t da, uint32_t db, int sc) {
    asm volatile("{\n.reg .pred p;\n.reg .b64 da, db;\nsetp.ne.b32 p, %100, 0;\n"
      "mov.b64 da, {%96, %97};\nmov.b64 db, {%98, %99};\n"
      "wgmma.mma_async.sync.aligned.m64n192k16.f32.bf16.bf16 {"
      "%0, %1, %2, %3, %4, %5, %6, %7, %8, %9, %10, %11, %12, %13, %14, %15, "
      "%16, %17, %18, %19, %20, %21, %22, %23, %24, %25, %26, %27, %28, %29, %30, %31, "
      "%32, %33, %34, %35, %36, %37, %38, %39, %40, %41, %42, %43, %44, %45, %46, %47, "
      "%48, %49, %50, %51, %52, %53, %54, %55, %56, %57, %58, %59, %60, %61, %62, %63, "
      "%64, %65, %66, %67, %68, %69, %70, %71, %72, %73, %74, %75, %76, %77, %78, %79, "
      "%80, %81, %82, %83, %84, %85, %86, %87, %88, %89, %90, %91, %92, %93, %94, %95"
      "}, da, db, p, 1, 1, 0, 1;\n}\n"
      : "+f"(d[0]), "+f"(d[1]), "+f"(d[2]), "+f"(d[3]), "+f"(d[4]), "+f"(d[5]), "+f"(d[6]), "+f"(d[7]),
        "+f"(d[8]), "+f"(d[9]), "+f"(d[10]), "+f"(d[11]), "+f"(d[12]), "+f"(d[13]), "+f"(d[14]), "+f"(d[15]),
        "+f"(d[16]), "+f"(d[17]), "+f"(d[18]), "+f"(d[19]), "+f"(d[20]), "+f"(d[21]), "+f"(d[22]), "+f"(d[23]),
        "+f"(d[24]), "+f"(d[25]), "+f"(d[26]), "+f"(d[27]), "+f"(d[28]), "+f"(d[29]), "+f"(d[30]), "+f"(d[31]),
        "+f"(d[32]), "+f"(d[33]), "+f"(d[34]), "+f"(d[35]), "+f"(d[36]), "+f"(d[37]), "+f"(d[38]), "+f"(d[39]),
        "+f"(d[40]), "+f"(d[41]), "+f"(d[42]), "+f"(d[43]), "+f"(d[44]), "+f"(d[45]), "+f"(d[46]), "+f"(d[47]),
        "+f"(d[48]), "+f"(d[49]), "+f"(d[50]), "+f"(d[51]), "+f"(d[52]), "+f"(d[53]), "+f"(d[54]), "+f"(d[55]),
        "+f"(d[56]), "+f"(d[57]), "+f"(d[58]), "+f"(d[59]), "+f"(d[60]), "+f"(d[61]), "+f"(d[62]), "+f"(d[63]),
        "+f"(d[64]), "+f"(d[65]), "+f"(d[66]), "+f"(d[67]), "+f"(d[68]), "+f"(d[69]), "+f"(d[70]), "+f"(d[71]),
        "+f"(d[72]), "+f"(d[73]), "+f"(d[74]), "+f"(d[75]), "+f"(d[76]), "+f"(d[77]), "+f"(d[78]), "+f"(d[79]),
        "+f"(d[80]), "+f"(d[81]), "+f"(d[82]), "+f"(d[83]), "+f"(d[84]), "+f"(d[85]), "+f"(d[86]), "+f"(d[87]),
        "+f"(d[88]), "+f"(d[89]), "+f"(d[90]), "+f"(d[91]), "+f"(d[92]), "+f"(d[93]), "+f"(d[94]), "+f"(d[95])
      : "r"(da), "n"(HA), "r"(db), "n"(HB), "r"(sc));
  }
};

struct FftConst {
  uint32_t f[2][4], fi[4][4];
  uint32_t ta[2][2], tb[2][2];
};
__device__ __forceinline__ void cis(int m, float scale, float& c, float& s) {
  const float a = (float)m * (-6.283185307179586f * scale);
  c = __cosf(a);
  s = __sinf(a);
}
__device__ __forceinline__ void fft_tables(uint32_t (&v)[12], int tw) {
  const int row = tw >> 2, ch = tw & 3;
#pragma unroll
  for (int i = 0; i < 4; i++) {
    float c[2], s[2], x[2];
#pragma unroll
    for (int e = 0; e < 2; e++) {
      cis((((32 * (8 * ch + 2 * i + e) + 15) * (4 * row - 63) + 2048) & 4095) - 2048, 1.f / 4096, c[e], s[e]);
      float gc, gs;
      cis((((row & 15) * (8 * (ch & 1) + 2 * i + e) + 8) & 15) - 8, 1.f / 16, gc, gs);
      x[e] = (row >> 4) == (ch >> 1) ? gc : (ch >> 1) ? gs : -gs;
    }
    v[i] = pack2(c[0] * 0.125f, c[1] * 0.125f);
    v[4 + i] = pack2(s[0] * 0.125f, s[1] * 0.125f);
    v[8 + i] = pack2(x[0], x[1]);
  }
#pragma unroll
  for (int i = 0; i < 12; i++) asm volatile("" : "+r"(v[i]));
}
__device__ __forceinline__ void fft_tables_store(const uint32_t (&v)[12], uint32_t sb, int tw) {
  const int row = tw >> 2;
  const uint32_t x = ((tw ^ (row >> 1)) & 3) << 4, a = sb + OFF_FT + (16 * (row >> 3) + (row & 7)) * 64 + x;
  sts128(a, v[0], v[1], v[2], v[3]);
  sts128(a + 512, v[4], v[5], v[6], v[7]);
  sts128(sb + OFF_GT + row * 64 + x, v[8], v[9], v[10], v[11]);
}
__device__ __forceinline__ void fft_twiddles(uint32_t (&v)[2], int tw) {
  float a[2], s[2];
#pragma unroll
  for (int i = 0; i < 2; i++) {
    float c;
    cis((2 * (2 * (tw & 3) + i) - 15) * (4 * (tw >> 2) - 63), 1.f / 4096, c, s[i]);
    a[i] = __fdividef(-s[i], 1.f + c);
  }
  v[0] = pack2(a[0], a[1]);
  v[1] = pack2(s[0], s[1]);
  asm volatile("" : "+r"(v[0]), "+r"(v[1]));
}
__device__ __forceinline__ void fft_matrices(FftConst& k, uint32_t sb, int w, int lane) {
  const uint32_t x = (lane >> 1) & 3;
  const uint2 t0 = lds64(sb + OFF_TT + 256 * w + 8 * lane), t1 = lds64(sb + OFF_TT + 256 * w + 8 * (lane ^ 3));
  k.ta[0][0] = t0.x;
  k.tb[0][0] = t0.y;
  k.ta[1][1] = __byte_perm(t1.x, 0, 0x1032);
  k.tb[1][1] = __byte_perm(t1.y, 0, 0x1032);
#pragma unroll
  for (int j = 0; j < 2; j++) {
    k.ta[1 - j][j] = k.ta[j][j] ^ 0x80008000u;
    k.tb[1 - j][j] = k.tb[j][j] ^ 0x80008000u;
    asm volatile("" : "+r"(k.ta[0][j]), "+r"(k.tb[0][j]), "+r"(k.ta[1][j]), "+r"(k.tb[1][j]));
  }
#pragma unroll
  for (int i = 0; i < 2; i++) {
    ldsm4(k.f[i], sb + OFF_FT + (16 * w + (lane & 15)) * 64 + (((2 * i + (lane >> 4)) ^ x) << 4));
    ldsm4t(k.fi[i], sb + OFF_FT + (32 * i + lane) * 64 + ((w ^ x) << 4));
#pragma unroll
    for (int j = 0; j < 4; j++) {
      k.fi[2 + i][j] = (j & 1) ? k.fi[i][j - 1] ^ 0x80008000u : k.fi[i][j + 1];
      asm volatile("" : "+r"(k.fi[2 + i][j]));
    }
  }
}
__device__ __forceinline__ void rot(uint32_t& x, uint32_t& y, uint32_t a, uint32_t b) {
  x = bfma(a, y, x);
  y = bfma(b, x, y);
  x = bfma(a, y, x);
}
__device__ __forceinline__ void twiddle_fwd(uint32_t (&a)[4][4], float* d, const FftConst& k) {
#pragma unroll
  for (int q = 0; q < 4; q++)
#pragma unroll
    for (int j = 0; j < 2; j++) {
      const float* x = d + 8 * q + 4 * j;
      uint32_t re = pack2(x[0], x[1]), im = pack2(x[2], x[3]);
      rot(re, im, k.ta[0][j], k.tb[0][j]);
      a[q & 2][2 * j + (q & 1)] = re;
      a[(q & 2) + 1][2 * j + (q & 1)] = im;
    }
}
__device__ __forceinline__ void g_step(float* d, const uint32_t (&a)[4][4], uint32_t dre, uint32_t dim) {
  WgRS<32>::set<HI_SW64>(d, a[0], dre);
  WgRS<32>::set<HI_SW64>(d + 16, a[2], dre);
  WgRS<32>::mma<HI_SW64>(d, a[1], dim);
  WgRS<32>::mma<HI_SW64>(d + 16, a[3], dim);
  wg_commit();
}

__device__ __forceinline__ void products(uint32_t (&a)[4][4], const float* H, const float* U, int p) {
#pragma unroll
  for (int j = 0; j < 2; j++)
#pragma unroll
    for (int m = 2 * p; m < 2 * p + 2; m++) {
      float pr[2], pi[2];
#pragma unroll
      for (int x = 0; x < 2; x++)
#pragma unroll
        for (int q = 0; q <= m; q++) {
          const int ih = 16 * (q >> 1) + 2 * (q & 1) + 4 * j + x, iu = 16 * ((m - q) >> 1) + 2 * ((m - q) & 1) + 4 * j + x;
          pr[x] = q ? fmaf(H[ih], U[iu], pr[x]) : H[ih] * U[iu];
          pi[x] = q ? fmaf(H[ih], U[iu + 8], pi[x]) : H[ih] * U[iu + 8];
          pr[x] = fmaf(-H[ih + 8], U[iu + 8], pr[x]);
          pi[x] = fmaf(H[ih + 8], U[iu], pi[x]);
        }
      a[m & 2][2 * j + (m & 1)] = pack2(pr[0], pr[1]);
      a[(m & 2) + 1][2 * j + (m & 1)] = pack2(pi[0], pi[1]);
    }
}

__device__ __forceinline__ void conv_channel(const FftConst& k, uint32_t sb, int c, int wg, int w, int lane) {
  const uint32_t cb = sb + off_ch(c), bars = sb + OFF_BAR;
  const uint32_t du = desc_lo(cb, 1024), dg = desc_lo(sb + OFF_GT, 16), dz = desc_lo(cb + U_BYTES, 16);
  float U[32], H[32];
  uint32_t a[4][4], e[4][4];
  const float dv = __uint_as_float(lds32(sb + OFF_D + 4 * c));
  wg_fence();
  WgRS<64>::set<HI_SW32>(H, k.f[0], du + 256);
  WgRS<64>::mma<HI_SW32>(H, k.f[1], du + 256 + 32);
  wg_commit();
  wg_wait<0>();
  pin<32>(H);
  twiddle_fwd(a, H, k);
  mbar_wait(bars + 8 * (B_U + (c < 3 ? c : 3)), 0);
  TSM(w == 0 && c < 3, 7 + wg);
  wg_fence();
  WgRS<64>::set<HI_SW32>(U, k.f[0], du);
  WgRS<64>::mma<HI_SW32>(U, k.f[1], du + 32);
  wg_commit();
  g_step(H, a, dg, dg + 64);
  wg_wait<1>();
  pin<32>(U);
  twiddle_fwd(e, U, k);
  wg_fence();
  g_step(U, e, dg, dg + 64);
  wg_wait<0>();
  pin<32>(U);
  pin<32>(H);
#pragma unroll
  for (int j = 0; j < 4; j++) H[4 * (j >> 1) + (j & 1)] += dv;
  float V[32];
#pragma unroll
  for (int p = 0; p < 2; p++) {
    products(a, H, U, p);
    wg_fence();
    WgRS<32>::set<HI_SW64>(V + 16 * p, a[2 * p], dg + 64);
    WgRS<32>::mma<HI_SW64>(V + 16 * p, a[2 * p + 1], dg);
    wg_commit();
  }
  const uint32_t za = cb + U_BYTES + (8 * w + (lane & 7)) * 128 + (((lane >> 3) ^ (lane & 7)) << 4);
  const uint32_t ya = cb + (lane >> 4) * 1024 + (8 * w + (lane & 7)) * 32 + ((((lane >> 3) ^ (lane >> 2)) & 1) << 4);
  wg_sync(1 + wg);
#pragma unroll
  for (int p = 0; p < 2; p++) {
    if (p == 0) wg_wait<1>();
    else wg_wait<0>();
    pin<16>(V + 16 * p);
#pragma unroll
    for (int i = 0; i < 4; i++) {
      const int j = i & 1;
      const float* x = V + 16 * p + 4 * j + (i & 2);
      e[p][i] = pack2(x[8], x[9]);
      e[2 + p][i] = pack2(x[0], x[1]);
      rot(e[p][i], e[2 + p][i], k.ta[1][j], k.tb[1][j]);
    }
    stsm4(za ^ (64 * p), e[p]);
    stsm4((za ^ (64 * p)) + 4096, e[2 + p]);
  }
  fence_async_smem();
  wg_sync(1 + wg);
  wg_fence();
  WgRS<64>::set<HI_SW128>(H, k.fi[0], dz);
#pragma unroll
  for (int ks = 1; ks < 4; ks++) WgRS<64>::mma<HI_SW128>(H, k.fi[ks], dz + 128 * ks);
  wg_commit();
  wg_wait<0>();
  pin<32>(H);
  if (lane == 0) mbar_arrive(bars + 8 * B_CVD);
  TSIF(w == 0, 88 + c);
#pragma unroll
  for (int j = 0; j < 8; j++)
    a[j >> 2][j & 3] = j < 2 ? pack2(H[4 * j], H[4 * j + 1]) : pack2(H[4 * j] + H[4 * j - 6], H[4 * j + 1] + H[4 * j - 5]);
  stsm4(ya, a[0]);
  stsm4(ya + 2048, a[1]);
  fence_async_smem();
  __syncwarp();
}

__device__ __forceinline__ void prep_slab(uint4* res, const uint2* sw, uint32_t sb, int slab, int w, int lane) {
  const int t = lane & 3, tp = (lane & 7) >> 1, pos = 8 * tp + 2 * (((lane >> 3) + tp) & 3) + (lane & 1);
  const uint32_t base = sb + OFF_KVS + slab * KVS_BYTES + pos * 128;
  uint32_t kk[2][4][4], vv[2][4];
  mbar_wait(sb + OFF_BAR + 8 * (B_KV + slab), 0);
#pragma unroll
  for (int h = 0; h < 2; h++) {
#pragma unroll
    for (int j = 0; j < 4; j++) {
      const uint32_t a = base + 128 * j;
      ldsm4t(kk[h][j], a + (((w + 4 * h) ^ ((a >> 7) & 7)) << 4));
    }
    const uint32_t a = base + KVS_V;
    ldsm4t(vv[h], a + (((w + 4 * h) ^ ((a >> 7) & 7)) << 4));
  }
#pragma unroll
  for (int h = 0; h < 2; h++) {
    uint32_t (&k)[4][4] = kk[h];
    uint32_t (&v)[4] = vv[h];
    const uint32_t w0 = __byte_perm(sw[h].x, 0, 0x1010), w1 = __byte_perm(sw[h].x, 0, 0x3232);
    const uint32_t w2 = __byte_perm(sw[h].y, 0, 0x1010), w3 = __byte_perm(sw[h].y, 0, 0x3232);
#pragma unroll
    for (int m = 0; m < 4; m++)
      v[m] = bmul(badd(badd(badd(bmul(k[0][m], w3), bmul(k[1][m], w2)), bmul(k[2][m], w1)), bmul(k[3][m], w0)), v[m]);
    uint32_t a[4];
#pragma unroll
    for (int m = 0; m < 4; m++) a[m] = (t & 1) ? v[(m + 3) & 3] : v[m];
    res[h] = (t & 2) ? make_uint4(a[2], a[3], a[0], a[1]) : make_uint4(a[0], a[1], a[2], a[3]);
  }
}

__device__ __forceinline__ void prep_gate(const Params& p, uint32_t sb, int b, int w, int lane) {
  uint2 gw[5], x[4][5];
#pragma unroll
  for (int j = 0; j < 5; j++) gw[j] = ldg64(reinterpret_cast<const uint2*>(p.gate_w) + lane + 32 * j);
#pragma unroll
  for (int i = 0; i < 4; i++)
#pragma unroll
    for (int j = 0; j < 5; j++)
      x[i][j] = ldg64(reinterpret_cast<const uint2*>(p.q) + (16 * b + 4 * w + i) * (DIM / 4) + lane + 32 * j);
  float s[4];
#pragma unroll
  for (int i = 0; i < 4; i++) {
    s[i] = 0.f;
#pragma unroll
    for (int j = 0; j < 5; j++) {
      const uint32_t m0 = bmul(x[i][j].x, gw[j].x), m1 = bmul(x[i][j].y, gw[j].y);
      s[i] += (bf_lo(m0) + bf_hi(m0)) + (bf_lo(m1) + bf_hi(m1));
    }
  }
  const bool h = lane & 16, q = lane & 8;
  const float a = (h ? s[2] : s[0]) + __shfl_xor_sync(0xffffffffu, h ? s[0] : s[2], 16);
  const float c = (h ? s[3] : s[1]) + __shfl_xor_sync(0xffffffffu, h ? s[1] : s[3], 16);
  float z = (q ? c : a) + __shfl_xor_sync(0xffffffffu, q ? a : c, 8);
#pragma unroll
  for (int o = 4; o > 0; o >>= 1) z += __shfl_xor_sync(0xffffffffu, z, o);
  z = bf_lo(pack2(z, 0.f));
  z = bf_lo(pack2(__fdividef(1.f, 1.f + __expf(-z)), 0.f));
  mbar_wait(sb + OFF_BAR + 8 * B_S3, 0);
  if ((lane & 7) == 0) asm volatile("st.shared.f32 [%0], %1;" ::"r"(sb + OFF_GATE + 64 * (b & 7) + 16 * w + (lane >> 1)), "f"(z) : "memory");
  fence_async_smem();
}

__device__ __forceinline__ uint32_t bmax(uint32_t a, uint32_t b) {
  uint32_t d;
  asm("max.bf16x2 %0, %1, %2;" : "=r"(d) : "r"(a), "r"(b));
  return d;
}
__device__ __forceinline__ void softmax_two(const float (&l)[2][2], uint32_t& p0, uint32_t& p1) {
  constexpr float kScale = 0.22360679774997896f, kLog2e = 1.4426950408889634f;
  const uint32_t r0 = pack2(l[0][0], l[1][0]), r1 = pack2(l[0][1], l[1][1]);
  const uint32_t x0 = pack2(bf_lo(r0) * kScale, bf_hi(r0) * kScale), x1 = pack2(bf_lo(r1) * kScale, bf_hi(r1) * kScale);
  uint32_t m = bmax(x0, x1);
  m = bmax(m, __shfl_xor_sync(0xffffffffu, m, 1));
  m = bmax(m, __shfl_xor_sync(0xffffffffu, m, 2));
  const float m0 = bf_lo(m) * kLog2e, m1 = bf_hi(m) * kLog2e;
  p0 = pack2(ex2(bf_lo(x0) * kLog2e - m0), ex2(bf_lo(x1) * kLog2e - m0));
  p1 = pack2(ex2(bf_hi(x0) * kLog2e - m1), ex2(bf_hi(x1) * kLog2e - m1));
}

__device__ __forceinline__ void halo_read(uint32_t (&kpv)[10], uint32_t (&vpv)[10], uint32_t (&tg)[7], const uint4* hp) {
#pragma unroll
  for (int j = 0; j < 7; j++) {
    uint32_t x0, x1, x2;
    asm volatile("ld.relaxed.gpu.global.v4.u32 {%0, %1, %2, %3}, [%4];"
                 : "=r"(x0), "=r"(x1), "=r"(x2), "=r"(tg[j]) : "l"(hp + 32 * j) : "memory");
    if (j < 4) kpv[3 * j] = x0; else vpv[3 * j - 10] = x0;
    if (j < 3) kpv[3 * j + 1] = x1; else vpv[3 * j - 9] = x1;
    if (j < 3) kpv[3 * j + 2] = x2; else if (j < 6) vpv[3 * j - 8] = x2;
  }
}

template <int ROT>
__device__ __forceinline__ void pack_qkv(const float* acc, uint32_t (&qlo)[10], uint32_t (&qhi)[10], uint32_t (&klo)[10],
                                         uint32_t (&khi)[10], uint32_t (&vlo)[10], uint32_t (&vhi)[10]) {
#pragma unroll
  for (int j = 0; j < 10; j++) {
    const int x = (j + ROT) % 10, tq = x < 8 ? x : 16 + x, tk = x < 8 ? 8 + x : 18 + x, tv = x < 8 ? 16 + x : 20 + x;
    khi[j] = pack2(acc[4 * tk + 2], acc[4 * tk + 3]);
    vhi[j] = movm(pack2(acc[4 * tv + 2], acc[4 * tv + 3]));
    qlo[j] = pack2(acc[4 * tq], acc[4 * tq + 1]);
    qhi[j] = pack2(acc[4 * tq + 2], acc[4 * tq + 3]);
    klo[j] = pack2(acc[4 * tk], acc[4 * tk + 1]);
    vlo[j] = pack2(acc[4 * tv], acc[4 * tv + 1]);
    asm volatile("" : "+r"(khi[j]), "+r"(qlo[j]), "+r"(qhi[j]), "+r"(klo[j]), "+r"(vlo[j]));
  }
}

template <int ROT> __device__ __forceinline__ void halo_send(const float* acc, uint4* ho, uint32_t tag) {
#pragma unroll
  for (int j = 0; j < 7; j++) {
    uint32_t x[3];
#pragma unroll
    for (int e = 0; e < 3; e++) {
      const int i = 3 * j + e, y = (i % 10 + ROT) % 10, tk = y < 8 ? 8 + y : 18 + y, tv = y < 8 ? 16 + y : 20 + y;
      x[e] = i < 10 ? pack2(acc[4 * tk + 2], acc[4 * tk + 3]) : i < 20 ? movm(pack2(acc[4 * tv + 2], acc[4 * tv + 3])) : 0u;
    }
    asm volatile("st.relaxed.gpu.global.v4.u32 [%0], {%1, %2, %3, %4};" ::"l"(ho + 32 * j), "r"(x[0]), "r"(x[1]), "r"(x[2]), "r"(tag) : "memory");
  }
}

__device__ __forceinline__ void attention(float* acc, uint32_t sb, int b, int par, int w, int lane, uint32_t tag, FftConst& fc) {
  const int g = lane >> 2, t = lane & 3;
  uint32_t klo[10], khi[10], vlo[10], vhi[10], qlo[10], qhi[10], kpv[10], vpv[10];
  if (w == 3 && b < NCTA - 8) {
    uint4* ho = g_halo + (b * 2 + par) * 224 + lane;
    if (tail_first(b & 7)) halo_send<8>(acc, ho, tag);
    else halo_send<0>(acc, ho, tag);
    TSIF(par == 0, 76);
    pin<120>(acc);
  }
  if (tail_first(b & 7)) pack_qkv<8>(acc, qlo, qhi, klo, khi, vlo, vhi);
  else pack_qkv<0>(acc, qlo, qhi, klo, khi, vlo, vhi);
  const uint32_t xa = sb + OFF_KVX + (par * 3) * 2560 + lane * 16;
  if (w < 3) {
    sts128(xa + w * 2560, khi[0], khi[1], khi[2], khi[3]);
    sts128(xa + w * 2560 + 512, khi[4], khi[5], khi[6], khi[7]);
    sts128(xa + w * 2560 + 1024, khi[8], khi[9], vhi[0], vhi[1]);
    sts128(xa + w * 2560 + 1536, vhi[2], vhi[3], vhi[4], vhi[5]);
    sts128(xa + w * 2560 + 2048, vhi[6], vhi[7], vhi[8], vhi[9]);
  }
  TSIF(par == 0 && w == 1, 64);
#pragma unroll
  for (int j = 0; j < 10; j++) vlo[j] = movm(vlo[j]);
  const bool far0 = 2 * t > g, far1 = 2 * t + 1 > g;
  const uint32_t mfar = (far0 ? 0x0000FFFFu : 0u) | (far1 ? 0xFFFF0000u : 0u);
  float slo[4][2], lg[2][2];
  uint32_t phi[4], plo[4], qml[4], qmh[4];
#pragma unroll
  for (int h = 0; h < 4; h++) {
    const int f = h == 0 ? 0 : h == 1 ? 3 : h == 2 ? 5 : 8, hf = h < 2 ? 2 : 7;
    const bool mine = (h & 1) ? t >= 2 : t < 2;
    qml[h] = mine ? qlo[hf] : 0u;
    qmh[h] = mine ? qhi[hf] : 0u;
    float a[4] = {0.f, 0.f, 0.f, 0.f}, c[4] = {0.f, 0.f, 0.f, 0.f};
    mma16816(a, qlo[f], qhi[f], qlo[f + 1], qhi[f + 1], klo[f], klo[f + 1]);
    mma16816(c, qlo[f], qhi[f], qlo[f + 1], qhi[f + 1], khi[f], khi[f + 1]);
    mma1688(a, qml[h], qmh[h], klo[hf]);
    mma1688(c, qml[h], qmh[h], khi[hf]);
    slo[h][0] = a[0];
    slo[h][1] = a[1];
    lg[h & 1][0] = far0 ? a[2] : c[2];
    lg[h & 1][1] = far1 ? a[3] : c[3];
    if (h & 1) softmax_two(lg, phi[h - 1], phi[h]);
  }
  TSIF(par == 0 && w == 1, 65);
  wg_sync(1 + par);
  TSIF(par == 0 && w == 1, 66);
  const bool nohist = (w == 0) && (b < 8);
  const uint4* hp = g_halo + ((b - 8) * 2 + par) * 224 + lane;
  uint32_t tg[7];
  if (w > 0) {
    const uint4 v0 = lds128(xa + (w - 1) * 2560), v1 = lds128(xa + (w - 1) * 2560 + 512), v2 = lds128(xa + (w - 1) * 2560 + 1024);
    const uint4 v3 = lds128(xa + (w - 1) * 2560 + 1536), v4 = lds128(xa + (w - 1) * 2560 + 2048);
    kpv[0] = v0.x; kpv[1] = v0.y; kpv[2] = v0.z; kpv[3] = v0.w; kpv[4] = v1.x; kpv[5] = v1.y; kpv[6] = v1.z; kpv[7] = v1.w;
    kpv[8] = v2.x; kpv[9] = v2.y; vpv[0] = v2.z; vpv[1] = v2.w; vpv[2] = v3.x; vpv[3] = v3.y; vpv[4] = v3.z; vpv[5] = v3.w;
    vpv[6] = v4.x; vpv[7] = v4.y; vpv[8] = v4.z; vpv[9] = v4.w;
  } else if (nohist) {
#pragma unroll
    for (int j = 0; j < 10; j++) kpv[j] = vpv[j] = 0u;
  } else {
    TSIF(par == 0, 77);
    halo_read(kpv, vpv, tg, hp);
  }
  if (w == 0 && !nohist) {
    int spins = 0;
    while (true) {
      bool ok = true;
#pragma unroll
      for (int j = 0; j < 7; j++) ok = ok && tg[j] == tag;
      if (__all_sync(0xffffffffu, ok) || ++spins > SPIN_LIMIT) break;
      halo_read(kpv, vpv, tg, hp);
    }
    TSIF(par == 0, 79);
  }
#pragma unroll
  for (int h = 0; h < 4; h++) {
    const int f = h == 0 ? 0 : h == 1 ? 3 : h == 2 ? 5 : 8, hf = h < 2 ? 2 : 7;
    float a[4] = {0.f, 0.f, 0.f, 0.f};
    mma16816(a, qlo[f], qhi[f], qlo[f + 1], qhi[f + 1], kpv[f], kpv[f + 1]);
    mma1688(a, qml[h], qmh[h], kpv[hf]);
    const float ninf = __int_as_float(0xff800000);
    lg[h & 1][0] = far0 ? (nohist ? ninf : a[0]) : slo[h][0];
    lg[h & 1][1] = far1 ? (nohist ? ninf : a[1]) : slo[h][1];
    if (h & 1) softmax_two(lg, plo[h - 1], plo[h]);
  }
  TSIF(par == 0 && w <= 1, 67 + w);
  mbar_wait(sb + OFF_BAR + 8 * B_HA, 0);
  fft_matrices(fc, sb, w, lane);
  uint32_t ov[20];
#pragma unroll
  for (int hp = 0; hp < 2; hp++) {
    const int hf = hp ? 7 : 2;
    float sh[4] = {0.f, 0.f, 0.f, 0.f}, i0 = 0.f, i1 = 0.f;
#pragma unroll
    for (int e = 0; e < 2; e++) {
      const int h = 2 * hp + e, f = h == 0 ? 0 : h == 1 ? 3 : h == 2 ? 5 : 8;
      const uint32_t a0 = plo[h] & mfar, a2 = plo[h] & ~mfar, a3 = phi[h] & mfar, c1 = phi[h] & ~mfar;
      float sum[4] = {0.f, 0.f, 0.f, 0.f};
      mma1688(sum, plo[h], phi[h], 0x3F803F80u);
      const float r0 = rcp(sum[0]), r1 = rcp(sum[2]);
#pragma unroll
      for (int j = f; j < f + 2; j++) {
        float o[4] = {0.f, 0.f, 0.f, 0.f};
        mma16816(o, a0, 0u, a2, a3, vpv[j], vlo[j]);
        mma1688(o, 0u, c1, vhi[j]);
        ov[2 * j] = pack2(o[0] * r0, o[1] * r0);
        ov[2 * j + 1] = pack2(o[2] * r1, o[3] * r1);
      }
      const bool mine = e ? g >= 4 : g < 4;
      mma16816(sh, a0, 0u, a2, a3, mine ? vpv[hf] : 0u, mine ? vlo[hf] : 0u);
      mma1688(sh, 0u, c1, mine ? vhi[hf] : 0u);
      if (e == 0 || t >= 2) {
        i0 = r0;
        i1 = r1;
      }
    }
    ov[2 * hf] = pack2(sh[0] * i0, sh[1] * i0);
    ov[2 * hf + 1] = pack2(sh[2] * i1, sh[3] * i1);
  }
  TS(32 + 4 * par + w);
  mbar_wait(sb + OFF_BAR + 8 * B_P1, 0);
  const uint32_t oa = sb + OFF_OA + (lane >> 4) * 2048 + (32 * w + 2 * (lane & 15) + par) * 16;
#pragma unroll
  for (int j = 0; j < 5; j++) stsm4(oa + 4096 * j, ov + 4 * j);
  TSIF(par == 0 && w == 0, 120);
  fence_async_smem();
  TSIF(par == 0 && w == 0, 121);
  __syncwarp();
  if (lane == 0) mbar_arrive(sb + OFF_BAR + 8 * B_ATTN);
  TSM(w == 0 || w == 2, 122 + par + (w == 2 ? 3 : 0));
}

struct Maps {
  CUtensorMap x, wm, wt, k, v, y, wo, qm, qt, om, ot, yl, ol, wh, ul;
};

__device__ __forceinline__ void load_stage(uint32_t sb, int kb, int b, const Maps& m) {
  const uint32_t st = sb + (kb & 3) * STAGE_BYTES, bar = sb + OFF_BAR + 8 * (B_FULL1 + (kb & 3));
  const int r = b >> 3, hg = b & 7, slab = kb - KV_KB;
  const bool kv = slab >= 0 && slab < 5;
  const uint32_t kbar = sb + OFF_BAR + 8 * (B_KV + slab), dst = sb + OFF_KVS + slab * KVS_BYTES;
  mbar_expect_tx(bar, STAGE_BYTES);
  if (kv) mbar_expect_tx(kbar, KVS_BYTES);
  tma_3d(st, &m.x, 64 * kb, 64 * r, 0, bar);
  tma_3d(st + ST_W, &m.wm, 80 * hg + (tail_first(hg) ? 16 : 0), 64 * kb, 0, bar);
  tma_3d(st + ST_WT, &m.wt, 80 * hg + (tail_first(hg) ? 0 : 64), 64 * kb, 0, bar);
  if (kv) tma_3d(dst, &m.k, 0, 32 * (b >> 1) - 3, 2 * slab + (b & 1), kbar);
  if (kv) tma_3d(dst + KVS_V, &m.v, 0, 32 * (b >> 1), 2 * slab + (b & 1), kbar);
}

__global__ void __launch_bounds__(NTHR, 1) fused_kernel(const __grid_constant__ Maps m, const Params p) {
  extern __shared__ __align__(1024) uint8_t smem[];
  const uint32_t sb = (uint32_t)__cvta_generic_to_shared(smem);
  const uint32_t bars = sb + OFF_BAR;
  const int tid = threadIdx.x, lane = tid & 31;
  int b = blockIdx.x;
  b = (((b & 63) >> 3) * 2 + (b & 1)) * 8 + (((b < 64 ? 0x6521 : 0x7430) >> (4 * ((b >> 1) & 3))) & 7);
  const int r = b >> 3, hg = b & 7;

  if (tid == T_ISSUE) {
    TSM(true, 0);
#pragma unroll
    for (int i = 0; i < 4; i++) mbar_init(bars + 8 * (B_F0 + i), 1);
    fence_async_smem();
#pragma unroll
    for (int i = 0; i < 4; i++) {
      mbar_expect_tx(bars + 8 * (B_F0 + i), (i ? 0 : ST_W) + 6144);
      if (i == 0) tma_3d(sb, &m.x, 0, 64 * r, 0, bars + 8 * B_F0);
      tma_3d(sb + ST_W + 6144 * i, &m.wh, 80 * hg + (tail_first(hg) ? 16 : 0), 16 * i, 0, bars + 8 * (B_F0 + i));
    }
#pragma unroll
    for (int i = 0; i < 4; i++) mbar_init(bars + 8 * (B_FULL1 + i), 1);
    fence_async_smem();
    mbar_expect_tx(bars + 8 * B_FULL1, STAGE_BYTES - ST_WT);
    tma_3d(sb + ST_WT, &m.wt, 80 * hg + (tail_first(hg) ? 0 : 64), 0, 0, bars + 8 * B_FULL1);
    load_stage(sb, 1, b, m);
  } else if (tid == T_INIT) {
#pragma unroll
    for (int i = 0; i < B_F0; i++) mbar_init(bars + 8 * i, i < B_GATE ? 8 : i < B_CVD ? 4 : i == B_CVD ? 20 : 1);
    fence_async_smem();
  }
  const int warp = __shfl_sync(0xffffffffu, tid >> 5, 0), wg = warp >> 2, w = warp & 3;
  __syncthreads();

  if (wg == 3) {
    asm volatile("setmaxnreg.dec.sync.aligned.u32 56;");
    if (w == 0) {
      if (lane == 0) {
#pragma unroll 1
        for (int kb = 2; kb < 10; kb++) {
          if (kb >= 4) mbar_wait(bars + 8 * (kb == 7 ? B_E3 : B_EMPTY1 + (kb & 3)), (kb >> 3) & 1);
          TSIF(kb >= 4, 44 + kb);
          load_stage(sb, kb, b, m);
          TSIF(kb == 3, 60);
          if (kb == 9) mbar_arrive(bars + 8 * B_LAST);
        }
        mbar_wait(bars + 8 * B_WOP, 0);
        mbar_wait(bars + 8 * B_EPOCH, 0);
        flag_wait(g_cnt + C_W + 32 * hg, (lds32(sb + OFF_EPOCH) + 1) * 16);
        TS(30);
#pragma unroll 1
        for (int j = 0; j < 8; j++) {
          if (j >= 6) mbar_wait(bars + 8 * (B_EMPTY2 + j - 6), 0);
          if (j == 4) mbar_wait(bars + 8 * B_ORB, 0);
          TSIF(j >= 6, 100 + j);
          mbar_expect_tx(bars + 8 * (B_FULL2 + j), j == 0 ? WO_BYTES : j == 5 ? O_BYTES + WO_BYTES + 512 : O_BYTES + WO_BYTES);
          bulk_load(sb + off_w(j), g_WO + (hg * 8 + step_src(hg, j)) * 800, WO_BYTES, bars + 8 * (B_FULL2 + j));
        }
        mbar_wait(bars + 8 * (B_EMPTY2 + 3), 0);
        mbar_expect_tx(bars + 8 * B_QF, O_BYTES);
        tma_2d(sb + OFF_QS, &m.qm, 80 * hg, 128 * r, bars + 8 * B_QF);
        tma_2d(sb + OFF_QT, &m.qt, 80 * hg + 64, 128 * r, bars + 8 * B_QF);
      }
    } else if (w == 1) {
      unsigned epoch = 0;
      if (lane == 0) {
        epoch = atomicAdd(g_cnt + C_LAUNCH, 1u) / NCTA;
        asm volatile("st.shared.u32 [%0], %1;" ::"r"(sb + OFF_EPOCH), "r"(epoch) : "memory");
        mbar_arrive(bars + 8 * B_EPOCH);
        mbar_wait(bars + 8 * B_KVD, 0);
        mbar_expect_tx(bars + 8 * B_HB, 5 * 4096);
#pragma unroll 1
        for (int c = 0; c < 5; c++) {
          if (c == 3) mbar_wait(bars + 8 * B_S3, 0);
          bulk_load(sb + off_ch(c) + U_BYTES, p.ssm_k + (5 * b + c) * SEQ, 4096, bars + 8 * B_HB);
        }
#pragma unroll
        for (int c = 0; c < 4; c++) mbar_expect_tx(bars + 8 * (B_U + c), c < 3 ? U_BYTES : 2 * U_BYTES);
        const uint4* usrc = g_U + 5 * b * U_PITCH;
        mbar_wait(bars + 8 * B_USIG, 0);
        flag_wait(g_cnt + C_PREP + 32 * (b & 15), (epoch + 1) * NCTA);
        TS(23);
#pragma unroll
        for (int c = 0; c < 5; c++) {
          if (c == 3) mbar_wait(bars + 8 * (B_U + 2), 0);
          bulk_load(sb + off_ch(c), usrc + c * U_PITCH, U_BYTES, bars + 8 * (B_U + (c < 3 ? c : 3)));
          TSIF(c == 0 || c == 4, 116 + (c >> 2));
        }
      }
      epoch = __shfl_sync(0xffffffffu, epoch, 0);
      if (lane < 8) {
        const int src = (b & ~7) | step_src(hg, lane);
        mbar_wait(bars + 8 * B_ATTN, 0);
        TS(20);
        bool seen = false;
#pragma unroll 1
        for (int spins = 0; spins < SPIN_LIMIT; spins++) {
          const bool now = !seen && (int)(flag_read(g_cnt + C_O + 32 * src) - (epoch + 1)) >= 0;
          if (now && lane >= 1 && lane < 4) bulk_load(sb + off_o(lane), g_O + src * 1280, O_BYTES, bars + 8 * (B_FULL2 + lane));
          seen = seen || now;
          if (__all_sync(0xff, seen)) break;
        }
        TS(21);
        if (lane == 5) bulk_load(sb + OFF_GATE, g_gate + 128 * r, 512, bars + 8 * (B_FULL2 + 5));
#pragma unroll 1
        for (int j = 4; j < 8; j++) {
          if (lane == j) {
            mbar_wait(bars + 8 * (j < 6 ? B_C34 : B_EMPTY2 + j - 6), 0);
            bulk_load(sb + off_o(j), g_O + src * 1280, O_BYTES, bars + 8 * (B_FULL2 + j));
          }
          __syncwarp(0xff);
        }
        TS(22);
      }
    } else if (w == 2) {
      mbar_wait(bars + 8 * B_PREP, 0);
      if (U_RB) {
        if (lane == 0) {
          mbar_expect_tx(bars + 8 * B_URB, 5 * 2048);
#pragma unroll 1
          for (int s = 0; s < 5; s++)
            tma_2d(sb + off_ch(s >> 1) + 2048 * (s & 1), &m.ul, 32 * (b >> 1) + 16, 128 * s + 64 * (b & 1), bars + 8 * B_URB);
          mbar_wait(bars + 8 * B_URB, 0);
        }
        __syncwarp();
        if (lane < 16) flag_bump(g_cnt + C_PREP + 32 * lane);
      } else {
        flag_signal(g_cnt + C_PREP, 16, lane);
      }
      TS(25);
      if (lane == 0) {
        mbar_arrive(bars + 8 * B_USIG);
        mbar_expect_tx(bars + 8 * B_ORB, O_BYTES / 4 + 64);
        mbar_wait(bars + 8 * B_GATE, 0);
        publish(g_gate + 16 * b, sb + OFF_GATE + 64 * hg, 64);
        bulk_load(sb + OFF_GATE + 64 * hg, g_gate + 16 * b, 64, bars + 8 * B_ORB);
        mbar_wait(bars + 8 * B_ATTN, 0);
        publish(g_O + b * 1280, sb + OFF_OA, O_BYTES);
        tma_2d(sb + OFF_KVX + 10240, &m.ol, 48, b * 160, bars + 8 * B_ORB);
        TS(74);
        mbar_wait(bars + 8 * B_ORB, 0);
        flag_bump(g_cnt + C_O + 32 * b);
        TS(26);
      }
    } else {
      if (lane == 0) {
        uint4* dst = g_WO + (hg * 8 + (r >> 1)) * 800 + (r & 1) * 80;
        mbar_wait(bars + 8 * B_S3, 0);
        asm volatile("cp.async.bulk.prefetch.L2.global [%0], 6400;" ::"l"(p.wo + b * 3200) : "memory");
        mbar_wait(bars + 8 * B_P1, 0);
        mbar_wait(bars + 8 * WB_TRIG, 0);
        mbar_expect_tx(bars + 8 * B_WST, WO_BYTES / 2);
        tma_3d(sb + OFF_WA, &m.wo, 0, 40 * r, 5 * hg, bars + 8 * B_WST);
        mbar_wait(bars + 8 * B_WST, 0);
#pragma unroll 1
        for (int n = 0; n < 5; n++) bulk_store(dst + 160 * n, sb + OFF_WA + 1280 * n, 1280);
        bulk_wait_read();
        mbar_expect_tx(bars + 8 * B_WST, WO_BYTES / 2);
#pragma unroll 1
        for (int n = 0; n < 5; n++) bulk_load(sb + OFF_WA + 1280 * n, dst + 160 * n, 1280, bars + 8 * B_WST);
        mbar_wait(bars + 8 * B_WST, 1);
        flag_bump(g_cnt + C_W + 32 * hg);
        mbar_arrive(bars + 8 * B_WOP);
        TS(71);
        mbar_expect_tx(bars + 8 * B_C34, 3 * (U_BYTES / 4));
        mbar_expect_tx(bars + 8 * B_YRB, 2 * (U_BYTES / 4));
#pragma unroll 1
        for (int c = 0; c < 5; c++) {
          mbar_wait(bars + 8 * (B_YST + c), 0);
          publish(g_U + (5 * b + c) * U_PITCH, sb + off_ch(c), U_BYTES);
          tma_2d(sb + off_ch(c), &m.yl, 48, (5 * b + c) * (U_PITCH / 8), bars + 8 * (c < 3 ? B_C34 : B_YRB));
        }
        TS(75);
        mbar_wait(bars + 8 * B_C34, 0);
        mbar_wait(bars + 8 * B_YRB, 0);
        flag_bump(g_cnt + C_Y + 32 * (b >> 4));
        TS(27);
        mbar_expect_tx(bars + 8 * B_YFULL, 20480);
        flag_wait(g_cnt + C_Y + 32 * hg, (lds32(sb + OFF_EPOCH) + 1) * 16);
        TS(24);
        tma_2d(sb + OFF_YT, &m.y, 128 * r, 80 * hg, bars + 8 * B_YFULL);
        tma_2d(sb + OFF_YT + 10240, &m.y, 128 * r + 64, 80 * hg, bars + 8 * B_YFULL);
      }
    }
  } else {
    asm volatile("setmaxnreg.inc.sync.aligned.u32 152;");
    FftConst fc;
    if (wg < 2) {
      float acc[120];
#pragma unroll
      for (int i = 0; i < 120; i++) acc[i] = 0.f;
      const uint32_t da = desc_lo(sb + wg * 8192, 16), db = desc_lo(sb + ST_W, 8192), dc = desc_lo(sb + ST_WT, 2048);
#pragma unroll
      for (int k = 0; k < 4; k++) {
        mbar_wait(bars + 8 * (B_F0 + k), 0);
        TSIF(w == 0 && wg == 0 && k == 0, 1);
        wg_fence();
        WgSST<192>::mma<HI_SW128, HI_SW128>(acc, da + 2 * k, desc_lo(sb + ST_W, 2048) + 384 * k, 1);
        wg_commit();
      }
      mbar_wait(bars + 8 * B_FULL1, 0);
      wg_fence();
#pragma unroll
      for (int k = 0; k < 4; k++) WgSST<48>::mma<HI_SW128, HI_SW32>(acc + 96, da + 2 * k, dc + 32 * k, 1);
      wg_commit();
#pragma unroll 1
      for (int kb = 1; kb < 10; kb++) {
        mbar_wait(bars + 8 * (B_FULL1 + (kb & 3)), (kb >> 2) & 1);
        const uint32_t so = (kb & 3) * (STAGE_BYTES >> 4);
        wg_fence();
#pragma unroll
        for (int k = 0; k < 4; k++) {
          WgSST<192>::mma<HI_SW128, HI_SW128>(acc, da + so + 2 * k, db + so + 128 * k, 1);
          WgSST<48>::mma<HI_SW128, HI_SW32>(acc + 96, da + so + 2 * k, dc + so + 32 * k, 1);
        }
        wg_commit();
        wg_wait<1>();
        if (lane == 0) mbar_arrive(bars + 8 * (kb == 4 ? B_E3 : B_EMPTY1 + ((kb - 1) & 3)));
      }
      mbar_wait(bars + 8 * B_EPOCH, 0);
      const uint32_t tag = lds32(sb + OFF_EPOCH) + 1;
      mbar_wait(bars + 8 * B_S3, 0);
      wg_wait<0>();
      pin<120>(acc);
      if (lane == 0) mbar_arrive(bars + 8 * B_P1);
      TSM(w == 0, 3 + wg);
      attention(acc, sb, b, wg, w, lane, tag, fc);
    } else {
      const int tw = tid & 127, chl = 64 * (b & 1) + 8 * w + (lane >> 2);
      uint4* up = g_U + chl * U_PITCH + ((4 * (b >> 1) + (lane & 3)) ^ ((b >> 2) & 1));
      uint2 sw[10];
      uint32_t dv = 0;
      if (lane < 5) dv = __ldg(reinterpret_cast<const unsigned short*>(p.ssm_D) + 5 * b + lane);
#pragma unroll
      for (int i = 0; i < 10; i++) sw[i] = ldg64(reinterpret_cast<const uint2*>(p.shift_k) + chl + 128 * (i >> 1) + 32 * (i & 1));
      uint32_t tab[12];
      uint32_t tt[2];
      fft_tables(tab, tw);
      fft_twiddles(tt, tw);
      uint4 res[10];
#pragma unroll
      for (int i = 0; i < 10; i++) res[i] = make_uint4(0, 0, 0, 0);
#pragma unroll 1
      for (int slab = 0; slab < 5; slab++) {
#pragma unroll
        for (int i = 0; i < 8; i++) res[i] = res[i + 2];
        prep_slab(res + 8, sw, sb, slab, w, lane);
        TSIF(w == 0, 99 + 4 * slab);
#pragma unroll
        for (int i = 0; i < 8; i++) sw[i] = sw[i + 2];
      }
      TSIF(w == 0, 28);
      __syncwarp();
      if (lane == 0) mbar_arrive(bars + 8 * B_KVD + ((res[8].x ^ res[9].x) & p.zero));
      mbar_wait(bars + 8 * B_KVD, 0);
      fft_tables_store(tab, sb, tw);
      mbar_wait(bars + 8 * B_LAST, 0);
#pragma unroll
      for (int i = 0; i < 10; i++) up[(128 * (i >> 1) + 32 * (i & 1)) * U_PITCH] = res[i];
      if (U_RB) asm volatile("fence.proxy.async.global;" ::: "memory");
      __syncwarp();
      if (lane == 0) mbar_arrive(bars + 8 * B_PREP);
      TSIF(w == 0, 5);
      mbar_wait(bars + 8 * B_LAST, 0);
      prep_gate(p, sb, b, w, lane);
      __syncwarp();
      if (lane == 0) mbar_arrive(bars + 8 * B_GATE);
      TSIF(w == 0, 72);
      mbar_wait(bars + 8 * B_HB, 0);
      TSIF(w == 0, 2);
      const uint32_t ha = sb + U_BYTES + ((tw >> 3) * 16 + 8 + (tw & 7)) * 16;
      uint4 hv[5];
#pragma unroll
      for (int c = 0; c < 5; c++) hv[c] = lds128(ha + off_ch(c));
      __syncwarp();
#pragma unroll
      for (int c = 0; c < 5; c++) sts128((ha ^ 16) + off_ch(c), hv[c].x, hv[c].y, hv[c].z, hv[c].w);
      asm volatile("st.shared.v2.u32 [%0], {%1, %2};" ::"r"(sb + OFF_TT + 8 * tw), "r"(tt[0]), "r"(tt[1]) : "memory");
      if (tw < 5) asm volatile("st.shared.f32 [%0], %1;" ::"r"(sb + OFF_D + 4 * tw), "f"(bf_lo(dv) * 0.125f) : "memory");
      fence_async_smem();
      __syncwarp();
      if (lane == 0) mbar_arrive(bars + 8 * B_HA);
      TSIF(w == 0, 6);
      mbar_wait(bars + 8 * B_HA, 0);
      fft_matrices(fc, sb, w, lane);
    }

    TSM(w == 0 && wg == 2, 124);
#pragma unroll 1
    for (uint32_t tasks = wg == 0 ? TASK0 : wg == 1 ? TASK1 : TASK2; tasks; tasks >>= 4) {
      const int c = (tasks & 7) - 1;
      conv_channel(fc, sb, c, wg, w, lane);
      if (lane == 0) mbar_arrive(bars + 8 * (B_YST + c));
      TSM(w == 0, 10 + c);
    }

    if (wg != 1) {
      const int wg = warp >> 3;
      const int g = lane >> 2;
      float acc[40];
#pragma unroll
      for (int i = 0; i < 40; i++) acc[i] = 0.f;
      const uint32_t da = desc_lo(sb + wg * 1024, 2048), db = desc_lo(sb, 2560);
      mbar_wait(bars + 8 * B_ORB, 0);
      mbar_wait(bars + 8 * B_FULL2, 0);
      TSM(w == 0, 15 + wg);
#pragma unroll 1
      for (int j = 0; j < 8; j++) {
        if (j == 1 - wg) mbar_wait(bars + 8 * B_CVD, 0);
        mbar_wait(bars + 8 * (B_FULL2 + j), 0);
        TSM(w == 0 && wg == 0, 44 + (j < 4 ? j : j + 6));
        const uint32_t oa = da + (off_o(j) >> 4), ob = db + (off_w(j) >> 4);
        wg_fence();
#pragma unroll
        for (int k = 0; k < 5; k++) WgSST<80>::mma<HI_NONE, HI_SW32>(acc, oa + 256 * k, ob + 32 * k, 1);
        wg_commit();
        wg_wait<1>();
        if (j >= 1 && j <= 4 && lane == 0) mbar_arrive(bars + 8 * (B_EMPTY2 + j - 1));
      }
      TSIF(w == 0 && wg == 0, 113);
      const int tr = 64 * wg + 16 * w + (lane & 15);
      const uint32_t fm = sb + OFF_QS + tr * 128, fx = (lane >> 4) ^ (tr & 7);
      const uint32_t ft = sb + OFF_QT + tr * 32 + (((lane >> 4) ^ (tr >> 2)) & 1) * 16;
      const float g0 = __uint_as_float(lds32(sb + OFF_GATE + (64 * wg + 16 * w + g) * 4));
      const float g1 = __uint_as_float(lds32(sb + OFF_GATE + (64 * wg + 16 * w + 8 + g) * 4));
      const uint32_t ga = pack2(g0, g0), gb = pack2(g1, g1);
      const uint32_t na = pack2(1.f - g0, 1.f - g0), nb = pack2(1.f - g1, 1.f - g1);

      uint32_t qf[20];
      mbar_wait(bars + 8 * B_QF, 0);
      TSM(w == 0 && wg == 0, 99);
#pragma unroll
      for (int j = 0; j < 5; j++) ldsm4(qf + 4 * j, j < 4 ? fm + ((fx ^ (2 * j)) << 4) : ft);
#pragma unroll
      for (int i = 0; i < 20; i++) {
        qf[i] = bmul((i & 1) ? gb : ga, qf[i]);
        asm volatile("" : "+r"(qf[i]));
      }

      wg_wait<0>();
      pin<40>(acc);
      TSM(w == 0, 17 + wg);
      uint32_t pb[20];
#pragma unroll
      for (int j = 0; j < 10; j++) {
        pb[2 * j] = bmul(na, pack2(acc[4 * j], acc[4 * j + 1]));
        pb[2 * j + 1] = bmul(nb, pack2(acc[4 * j + 2], acc[4 * j + 3]));
        asm volatile("" : "+r"(pb[2 * j]), "+r"(pb[2 * j + 1]));
      }
      const uint32_t ya = sb + OFF_YT + wg * 10240 + ((lane >> 4) * 8 + (lane & 7)) * 128 +
                          (((2 * w + (((lane >> 3) & 1) ^ wg)) ^ (lane & 7)) << 4);
      mbar_wait(bars + 8 * B_YFULL, 0);
      TSM(w == 0 && wg == 0, 19);
#pragma unroll
      for (int j = 0; j < 5; j++) {
        uint32_t y[4];
        ldsm4t(y, ya + 2048 * j);
#pragma unroll
        for (int i = 0; i < 4; i++)
          qf[4 * j + i] = bfma(qf[4 * j + i], y[i], pb[4 * j + i]);
      }
#pragma unroll
      for (int j = 0; j < 5; j++) stsm4(j < 4 ? fm + ((fx ^ (2 * j)) << 4) : ft, qf + 4 * j);
      fence_async_smem();
      __syncwarp();
      if (lane == 0) {
        const int row = 64 * wg + 16 * w;
        asm volatile("cp.async.bulk.tensor.2d.global.shared::cta.bulk_group [%0, {%2, %3}], [%1];"
                     ::"l"(&m.om), "r"(sb + OFF_QS + row * 128), "r"(80 * hg), "r"(128 * r + row) : "memory");
        asm volatile("cp.async.bulk.tensor.2d.global.shared::cta.bulk_group [%0, {%2, %3}], [%1];"
                     ::"l"(&m.ot), "r"(sb + OFF_QT + row * 32), "r"(80 * hg + 64), "r"(128 * r + row) : "memory");
        asm volatile("cp.async.bulk.commit_group;\ncp.async.bulk.wait_group.read 0;" ::: "memory");
      }
      TSM(w == 0 || w == 3, 40 + 2 * wg + (w & 1));
    }
  }
}

typedef CUresult (*EncodeFn)(CUtensorMap*, CUtensorMapDataType, cuuint32_t, void*, const cuuint64_t*, const cuuint64_t*,
                             const cuuint32_t*, const cuuint32_t*, CUtensorMapInterleave, CUtensorMapSwizzle,
                             CUtensorMapL2promotion, CUtensorMapFloatOOBfill);

void encode(EncodeFn fn, CUtensorMap* tm, const void* base, int rank, const cuuint64_t* dims, const cuuint64_t* strides,
            const cuuint32_t* box, CUtensorMapSwizzle swz, CUtensorMapL2promotion promo = CU_TENSOR_MAP_L2_PROMOTION_L2_128B) {
  const cuuint32_t ones[3] = {1, 1, 1};
  fn(tm, CU_TENSOR_MAP_DATA_TYPE_BFLOAT16, rank, const_cast<void*>(base), dims, strides, box, ones,
     CU_TENSOR_MAP_INTERLEAVE_NONE, swz, promo, CU_TENSOR_MAP_FLOAT_OOB_FILL_NONE);
}

}

extern "C" void kernel_launch(void* const* d_in, const int* in_sizes, int n_in, void* d_out, int out_size) {
  (void)in_sizes; (void)n_in; (void)out_size;
  Params p;
  p.q = (const __nv_bfloat16*)d_in[0];
  p.k = (const __nv_bfloat16*)d_in[1];
  p.v = (const __nv_bfloat16*)d_in[2];
  p.shift_k = (const __nv_bfloat16*)d_in[3];
  p.ssm_k = (const __nv_bfloat16*)d_in[4];
  p.ssm_D = (const __nv_bfloat16*)d_in[5];
  p.wqkv = (const __nv_bfloat16*)d_in[7];
  p.wo = (const __nv_bfloat16*)d_in[8];
  p.gate_w = (const __nv_bfloat16*)d_in[9];
  p.out = (__nv_bfloat16*)d_out;
  p.zero = 0;

  static EncodeFn fn = nullptr;
  static void *yaddr = nullptr, *oaddr = nullptr;
  if (!fn) {
    cudaDriverEntryPointQueryResult qr;
    void* f = nullptr;
    cudaGetDriverEntryPoint("cuTensorMapEncodeTiled", &f, cudaEnableDefault, &qr);
    fn = (EncodeFn)f;
    cudaGetSymbolAddress(&yaddr, g_U);
    cudaGetSymbolAddress(&oaddr, g_O);
    cudaFuncSetAttribute(fused_kernel, cudaFuncAttributeMaxDynamicSharedMemorySize, SMEM_BYTES);
  }
  Maps m;
  {
    const cuuint64_t dims[3] = {640, 1024, 2}, st[2] = {2560, 1280};
    const cuuint32_t box[3] = {64, 64, 2};
    encode(fn, &m.x, p.q, 3, dims, st, box, CU_TENSOR_MAP_SWIZZLE_128B);
  }
  {
    const cuuint64_t dims[3] = {640, 640, 3}, st[2] = {3840, 1280};
    const cuuint32_t box[3] = {64, 64, 3}, boxt[3] = {16, 64, 3};
    encode(fn, &m.wm, p.wqkv, 3, dims, st, box, CU_TENSOR_MAP_SWIZZLE_128B);
    encode(fn, &m.wt, p.wqkv, 3, dims, st, boxt, CU_TENSOR_MAP_SWIZZLE_32B);
    const cuuint32_t boxh[3] = {64, 16, 3};
    encode(fn, &m.wh, p.wqkv, 3, dims, st, boxh, CU_TENSOR_MAP_SWIZZLE_128B);
  }
  {
    const cuuint64_t dims[3] = {64, 2048, 10}, st[2] = {1280, 128};
    const cuuint32_t boxk[3] = {64, 35, 1}, boxv[3] = {64, 32, 1};
    encode(fn, &m.k, p.k, 3, dims, st, boxk, CU_TENSOR_MAP_SWIZZLE_128B);
    encode(fn, &m.v, p.v, 3, dims, st, boxv, CU_TENSOR_MAP_SWIZZLE_128B);
  }
  {
    const cuuint64_t dims[3] = {16, 640, 40}, st[2] = {1280, 32};
    const cuuint32_t box[3] = {16, 40, 5};
    encode(fn, &m.wo, p.wo, 3, dims, st, box, CU_TENSOR_MAP_SWIZZLE_32B);
  }
  {
    const cuuint64_t dims[2] = {2048, 640}, st[1] = {U_PITCH * 16};
    const cuuint32_t box[2] = {64, 80};
    encode(fn, &m.y, yaddr, 2, dims, st, box, CU_TENSOR_MAP_SWIZZLE_128B);
    const cuuint64_t dl[2] = {64, DIM * U_PITCH / 8}, dol[2] = {64, NCTA * 160}, sl[1] = {128};
    const cuuint32_t bl[2] = {16, 32}, bol[2] = {16, 160};
    const cuuint32_t bu[2] = {16, 64};
    encode(fn, &m.ul, yaddr, 2, dims, st, bu, CU_TENSOR_MAP_SWIZZLE_NONE, CU_TENSOR_MAP_L2_PROMOTION_NONE);
    encode(fn, &m.yl, yaddr, 2, dl, sl, bl, CU_TENSOR_MAP_SWIZZLE_NONE);
    encode(fn, &m.ol, oaddr, 2, dol, sl, bol, CU_TENSOR_MAP_SWIZZLE_NONE);
  }
  {
    const cuuint64_t dims[2] = {640, 2048}, st[1] = {1280};
    const cuuint32_t bqm[2] = {64, 128}, bqt[2] = {16, 128}, bom[2] = {64, 16}, bot[2] = {16, 16};
    encode(fn, &m.qm, p.q, 2, dims, st, bqm, CU_TENSOR_MAP_SWIZZLE_128B);
    encode(fn, &m.qt, p.q, 2, dims, st, bqt, CU_TENSOR_MAP_SWIZZLE_32B);
    encode(fn, &m.om, p.out, 2, dims, st, bom, CU_TENSOR_MAP_SWIZZLE_128B);
    encode(fn, &m.ot, p.out, 2, dims, st, bot, CU_TENSOR_MAP_SWIZZLE_32B);
  }
  fused_kernel<<<NCTA, NTHR, SMEM_BYTES>>>(m, p);
}
```

```cpp
#include <cuda.h>
#include <cuda_bf16.h>
#include <cuda_runtime.h>
#include <stdint.h>

namespace {

constexpr int SEQ = 2048, DIM = 640, NCTA = 128, NTHR = 512;

#define KV_KB 2
#define DEV_EXIT 0
#define FENCE_LO 0
#define FENCE_HI 0
#define WB_TRIG B_USIG
#define T_ISSUE 288
#define T_INIT 448
#define TASK0 0x3
#define TASK1 0x52
#define TASK2 0x41

constexpr uint32_t STAGE_BYTES = 47104, ST_W = 16384, ST_WT = 40960;
constexpr uint32_t O_BYTES = 20480, WO_BYTES = 12800;
constexpr uint32_t OFF_OA = 0;
constexpr uint32_t OFF_QS = 3 * O_BYTES, OFF_QT = OFF_QS + 16384;
constexpr uint32_t OFF_WC = 81920;
constexpr uint32_t OFF_WA = 94720;
constexpr uint32_t OFF_GATE = 145920;
constexpr uint32_t OFF_TT = 146432;
constexpr uint32_t OFF_KVX = 148480;
constexpr uint32_t OFF_CH3 = 163840;
constexpr uint32_t CH_BYTES = 12288, U_BYTES = 4096;
constexpr uint32_t OFF_FT = 225280, OFF_GT = 229376;
constexpr uint32_t OFF_CH0 = 188416;
constexpr uint32_t OFF_KVS = OFF_CH0, KVS_V = 4480, KVS_BYTES = 8576;
constexpr uint32_t OFF_YT = 163840;
constexpr uint32_t OFF_BAR = 231936;
constexpr uint32_t SMEM_BYTES = OFF_BAR + 512;

enum : uint32_t {
  B_EMPTY1 = 0, B_S3 = 3, B_E3 = 4, B_EMPTY2 = 5, B_ATTN = 9, B_P1 = 10,
  B_GATE = 11, B_HA = 12, B_KVD = 13, B_PREP = 14, B_YST = 15,
  B_CVD = 20,
  B_FULL2 = 21, B_U = 29, B_KV = 33, B_HB = 38, B_C34 = 39, B_YRB = 40, B_YFULL = 41, B_EPOCH = 42, B_LAST = 43,
  B_WOP = 44, B_USIG = 45, B_WST = 46, B_QF = 47, B_ORB = 48,
  B_F0 = 49, B_FULL1 = 53
};
constexpr uint32_t OFF_EPOCH = OFF_BAR + 8 * 58, OFF_D = OFF_BAR + 8 * 60;
__device__ __forceinline__ uint32_t off_o(int j) { return j < 4 ? OFF_OA + j * O_BYTES : j < 6 ? OFF_CH0 + (j - 4) * O_BYTES : OFF_OA + (j - 6) * O_BYTES; }
__device__ __forceinline__ uint32_t off_w(int j) { return j < 4 ? OFF_WA + j * WO_BYTES : j == 4 ? OFF_KVX : j == 5 ? OFF_WC : OFF_WA + (j - 6) * WO_BYTES; }
__device__ __forceinline__ int step_src(int hg, int j) { return j == 0 ? hg : j <= hg ? j - 1 : j; }
__device__ __forceinline__ bool tail_first(int hg) { return (hg & 3) == 3; }
__device__ __forceinline__ uint32_t off_ch(int c) { return (c < 3 ? OFF_CH0 : OFF_CH3 - 3 * CH_BYTES) + c * CH_BYTES; }

#define U_PITCH 264
__device__ __align__(1024) uint4 g_U[DIM * U_PITCH];
__device__ __align__(128) uint4 g_O[NCTA * 1280];
__device__ __align__(128) uint4 g_WO[64 * 800];
__device__ __align__(128) uint4 g_halo[NCTA * 2 * 7 * 32];
__device__ __align__(128) float g_gate[SEQ];
__device__ __align__(128) unsigned g_cnt[32 * (1 + 2 * 16 + 8 + NCTA)];
constexpr int C_LAUNCH = 0, C_PREP = 32, C_Y = 32 * 17, C_W = 32 * 33, C_O = 32 * 41;

#define TSM(cond, slot) do { } while (0)
#define TSIF(cond, slot) do { if (__LINE__ >= FENCE_LO && __LINE__ < FENCE_HI) sched_fence(); } while (0)
__device__ __forceinline__ void sched_fence() {
  asm volatile("{\n.reg .pred p;\n.reg .u32 c;\nmov.u32 c, %%clock;\nsetp.eq.u32 p, c, 0;\n@p st.shared.u32 [%0], c;\n}"
               ::"r"(1024 + OFF_EPOCH + 4) : "memory");
}
#define TS(slot) TSIF(true, slot)

struct Params {
  const __nv_bfloat16 *q, *k, *v, *shift_k, *ssm_k, *ssm_D, *wqkv, *wo, *gate_w;
  __nv_bfloat16* out;
  uint32_t zero;
};

constexpr int SPIN_LIMIT = 1 << 17;

__device__ __forceinline__ void mbar_init(uint32_t bar, uint32_t count) {
  asm volatile("mbarrier.init.shared::cta.b64 [%0], %1;" ::"r"(bar), "r"(count) : "memory");
}
__device__ __forceinline__ void mbar_expect_tx(uint32_t bar, uint32_t bytes) {
  asm volatile("mbarrier.arrive.expect_tx.shared::cta.b64 _, [%0], %1;" ::"r"(bar), "r"(bytes) : "memory");
}
__device__ __forceinline__ void mbar_arrive(uint32_t bar) {
  asm volatile("mbarrier.arrive.shared::cta.b64 _, [%0];" ::"r"(bar) : "memory");
}
__device__ __forceinline__ void mbar_wait(uint32_t bar, uint32_t parity) {
  uint32_t ok;
  int spins = 0;
  do {
      asm volatile("{\n.reg .pred p;\nmbarrier.try_wait.parity.shared::cta.b64 p, [%1], %2;\nselp.b32 %0, 1, 0, p;\n}"
                   : "=r"(ok) : "r"(bar), "r"(parity) : "memory");
    if (++spins > SPIN_LIMIT) break;
  } while (!ok);
}
__device__ __forceinline__ unsigned flag_read(const unsigned* p) {
  unsigned v;
  asm volatile("ld.relaxed.gpu.global.u32 %0, [%1];" : "=r"(v) : "l"(p) : "memory");
  return v;
}
__device__ __forceinline__ void flag_poll(const unsigned* p, unsigned target) {
  unsigned v;
  int spins = 0;
  do {
    asm volatile("ld.relaxed.gpu.global.u32 %0, [%1];" : "=r"(v) : "l"(p) : "memory");
    if (++spins > SPIN_LIMIT) break;
  } while ((int)(v - target) < 0);
}
__device__ __forceinline__ void flag_wait(const unsigned* p, unsigned target) {
  flag_poll(p, target);
}
__device__ __forceinline__ void flag_signal(unsigned* p, int n, int lane) {
  if (lane == 0) asm volatile("fence.release.gpu;" ::: "memory");
  __syncwarp();
  if (lane < n) asm volatile("red.relaxed.gpu.global.add.u32 [%0], 1;" ::"l"(p + 32 * lane) : "memory");
}
__device__ __forceinline__ void flag_bump(unsigned* p) {
  asm volatile("red.relaxed.gpu.global.add.u32 [%0], 1;" ::"l"(p) : "memory");
}
__device__ __forceinline__ void fence_async_smem() { asm volatile("fence.proxy.async.shared::cta;" ::: "memory"); }
__device__ __forceinline__ void wg_sync(int id) { asm volatile("bar.sync %0, 128;" ::"r"(id) : "memory"); }

__device__ __forceinline__ void tma_2d(uint32_t dst, const CUtensorMap* tm, int c0, int c1, uint32_t bar) {
  asm volatile("cp.async.bulk.tensor.2d.shared::cluster.global.mbarrier::complete_tx::bytes [%0], [%1, {%3, %4}], [%2];"
               ::"r"(dst), "l"(tm), "r"(bar), "r"(c0), "r"(c1) : "memory");
}
__device__ __forceinline__ void tma_3d(uint32_t dst, const CUtensorMap* tm, int c0, int c1, int c2, uint32_t bar) {
  asm volatile("cp.async.bulk.tensor.3d.shared::cluster.global.mbarrier::complete_tx::bytes [%0], [%1, {%3, %4, %5}], [%2];"
               ::"r"(dst), "l"(tm), "r"(bar), "r"(c0), "r"(c1), "r"(c2) : "memory");
}
__device__ __forceinline__ void bulk_load(uint32_t dst, const void* src, uint32_t bytes, uint32_t bar) {
  asm volatile("cp.async.bulk.shared::cluster.global.mbarrier::complete_tx::bytes [%0], [%1], %2, [%3];"
               ::"r"(dst), "l"(src), "r"(bytes), "r"(bar) : "memory");
}
__device__ __forceinline__ void bulk_store(void* dst, uint32_t src, uint32_t bytes) {
  asm volatile("cp.async.bulk.global.shared::cta.bulk_group [%0], [%1], %2;" ::"l"(dst), "r"(src), "r"(bytes) : "memory");
}
__device__ __forceinline__ void bulk_wait_read() {
  asm volatile("cp.async.bulk.commit_group;\ncp.async.bulk.wait_group.read 0;" ::: "memory");
}

__device__ __forceinline__ void publish(void* dst, uint32_t src, uint32_t bytes) {
  bulk_store(dst, src, bytes);
  bulk_wait_read();
}

__device__ __forceinline__ void wg_fence() { asm volatile("wgmma.fence.sync.aligned;" ::: "memory"); }
__device__ __forceinline__ void wg_commit() { asm volatile("wgmma.commit_group.sync.aligned;" ::: "memory"); }
template <int N> __device__ __forceinline__ void wg_wait() { asm volatile("wgmma.wait_group.sync.aligned %0;" ::"n"(N) : "memory"); }
__device__ __forceinline__ uint32_t desc_lo(uint32_t addr, uint32_t lbo) { return ((addr & 0x3FFFF) >> 4) | ((lbo >> 4) << 16); }
constexpr uint32_t desc_hi(uint32_t sbo, uint32_t swz) { return (sbo >> 4) | (swz << 30); }
constexpr uint32_t HI_SW128 = desc_hi(1024, 1), HI_SW64 = desc_hi(512, 2), HI_SW32 = desc_hi(256, 3), HI_NONE = desc_hi(128, 0);
template <int N> __device__ __forceinline__ void pin(float* d) {
#pragma unroll
  for (int i = 0; i < N; i++) asm volatile("" : "+f"(d[i])::"memory");
}

__device__ __forceinline__ uint32_t lds32(uint32_t a) {
  uint32_t v;
  asm volatile("ld.volatile.shared.u32 %0, [%1];" : "=r"(v) : "r"(a) : "memory");
  return v;
}
__device__ __forceinline__ uint2 ldg64(const void* a) {
  uint2 v;
  asm volatile("ld.global.nc.v2.u32 {%0, %1}, [%2];" : "=r"(v.x), "=r"(v.y) : "l"(a) : "memory");
  return v;
}
__device__ __forceinline__ void ldsm4(uint32_t* r, uint32_t a) {
  asm volatile("ldmatrix.sync.aligned.m8n8.x4.shared.b16 {%0, %1, %2, %3}, [%4];"
               : "=r"(r[0]), "=r"(r[1]), "=r"(r[2]), "=r"(r[3]) : "r"(a) : "memory");
}
__device__ __forceinline__ void ldsm4t(uint32_t* r, uint32_t a) {
  asm volatile("ldmatrix.sync.aligned.m8n8.x4.trans.shared.b16 {%0, %1, %2, %3}, [%4];"
               : "=r"(r[0]), "=r"(r[1]), "=r"(r[2]), "=r"(r[3]) : "r"(a) : "memory");
}
__device__ __forceinline__ uint2 lds64(uint32_t a) {
  uint2 v;
  asm volatile("ld.shared.v2.u32 {%0, %1}, [%2];" : "=r"(v.x), "=r"(v.y) : "r"(a) : "memory");
  return v;
}
__device__ __forceinline__ uint4 lds128(uint32_t a) {
  uint4 v;
  asm volatile("ld.shared.v4.u32 {%0, %1, %2, %3}, [%4];" : "=r"(v.x), "=r"(v.y), "=r"(v.z), "=r"(v.w) : "r"(a) : "memory");
  return v;
}
__device__ __forceinline__ void sts128(uint32_t a, uint32_t x, uint32_t y, uint32_t z, uint32_t w) {
  asm volatile("st.shared.v4.u32 [%0], {%1, %2, %3, %4};" ::"r"(a), "r"(x), "r"(y), "r"(z), "r"(w) : "memory");
}
__device__ __forceinline__ void stsm4(uint32_t a, const uint32_t* r) {
  asm volatile("stmatrix.sync.aligned.m8n8.x4.shared.b16 [%0], {%1, %2, %3, %4};" ::"r"(a), "r"(r[0]), "r"(r[1]), "r"(r[2]), "r"(r[3]) : "memory");
}
__device__ __forceinline__ uint32_t pack2(float lo, float hi) {
  uint32_t r;
  asm("cvt.rn.bf16x2.f32 %0, %1, %2;" : "=r"(r) : "f"(hi), "f"(lo));
  return r;
}
__device__ __forceinline__ uint32_t movm(uint32_t a) {
  uint32_t d;
  asm volatile("movmatrix.sync.aligned.m8n8.trans.b16 %0, %1;" : "=r"(d) : "r"(a));
  return d;
}
__device__ __forceinline__ uint32_t bmul(uint32_t a, uint32_t b) {
  uint32_t d;
  asm("mul.rn.bf16x2 %0, %1, %2;" : "=r"(d) : "r"(a), "r"(b));
  return d;
}
__device__ __forceinline__ uint32_t badd(uint32_t a, uint32_t b) {
  uint32_t d;
  asm("add.rn.bf16x2 %0, %1, %2;" : "=r"(d) : "r"(a), "r"(b));
  return d;
}
__device__ __forceinline__ uint32_t bfma(uint32_t a, uint32_t b, uint32_t c) {
  uint32_t d;
  asm("fma.rn.bf16x2 %0, %1, %2, %3;" : "=r"(d) : "r"(a), "r"(b), "r"(c));
  return d;
}
__device__ __forceinline__ float bf_lo(uint32_t x) { return __uint_as_float(x << 16); }
__device__ __forceinline__ float bf_hi(uint32_t x) { return __uint_as_float(x & 0xFFFF0000u); }
__device__ __forceinline__ float ex2(float x) {
  float y;
  asm("ex2.approx.ftz.f32 %0, %1;" : "=f"(y) : "f"(x));
  return y;
}
__device__ __forceinline__ float rcp(float x) {
  float y;
  asm("rcp.approx.ftz.f32 %0, %1;" : "=f"(y) : "f"(x));
  return y;
}
__device__ __forceinline__ void mma16816(float* d, uint32_t a0, uint32_t a1, uint32_t a2, uint32_t a3, uint32_t b0, uint32_t b1) {
  asm volatile("mma.sync.aligned.m16n8k16.row.col.f32.bf16.bf16.f32 {%0, %1, %2, %3}, {%4, %5, %6, %7}, {%8, %9}, {%0, %1, %2, %3};"
               : "+f"(d[0]), "+f"(d[1]), "+f"(d[2]), "+f"(d[3])
               : "r"(a0), "r"(a1), "r"(a2), "r"(a3), "r"(b0), "r"(b1));
}
__device__ __forceinline__ void mma1688(float* d, uint32_t a0, uint32_t a1, uint32_t b0) {
  asm volatile("mma.sync.aligned.m16n8k8.row.col.f32.bf16.bf16.f32 {%0, %1, %2, %3}, {%4, %5}, {%6}, {%0, %1, %2, %3};"
               : "+f"(d[0]), "+f"(d[1]), "+f"(d[2]), "+f"(d[3])
               : "r"(a0), "r"(a1), "r"(b0));
}

template <int N> struct WgRS;
template <int N> struct WgSST;
template <> struct WgRS<32> {
  template <uint32_t HB>
  static __device__ __forceinline__ void mma(float* d, const uint32_t* a, uint32_t db) {
    asm volatile("{\n.reg .pred p;\n.reg .b64 db;\nsetp.ne.b32 p, %22, 0;\n"
      "mov.b64 db, {%20, %21};\n"
      "wgmma.mma_async.sync.aligned.m64n32k16.f32.bf16.bf16 {"
      "%0, %1, %2, %3, %4, %5, %6, %7, %8, %9, %10, %11, %12, %13, %14, %15"
      "}, {%16, %17, %18, %19}, db, p, 1, 1, 1;\n}\n"
      : "+f"(d[0]), "+f"(d[1]), "+f"(d[2]), "+f"(d[3]), "+f"(d[4]), "+f"(d[5]), "+f"(d[6]), "+f"(d[7]),
        "+f"(d[8]), "+f"(d[9]), "+f"(d[10]), "+f"(d[11]), "+f"(d[12]), "+f"(d[13]), "+f"(d[14]), "+f"(d[15])
      : "r"(a[0]), "r"(a[1]), "r"(a[2]), "r"(a[3]), "r"(db), "n"(HB), "n"(1));
  }
  template <uint32_t HB>
  static __device__ __forceinline__ void set(float* d, const uint32_t* a, uint32_t db) {
    asm volatile("{\n.reg .pred p;\n.reg .b64 db;\nsetp.ne.b32 p, %22, 0;\n"
      "mov.b64 db, {%20, %21};\n"
      "wgmma.mma_async.sync.aligned.m64n32k16.f32.bf16.bf16 {"
      "%0, %1, %2, %3, %4, %5, %6, %7, %8, %9, %10, %11, %12, %13, %14, %15"
      "}, {%16, %17, %18, %19}, db, p, 1, 1, 1;\n}\n"
      : "=f"(d[0]), "=f"(d[1]), "=f"(d[2]), "=f"(d[3]), "=f"(d[4]), "=f"(d[5]), "=f"(d[6]), "=f"(d[7]),
        "=f"(d[8]), "=f"(d[9]), "=f"(d[10]), "=f"(d[11]), "=f"(d[12]), "=f"(d[13]), "=f"(d[14]), "=f"(d[15])
      : "r"(a[0]), "r"(a[1]), "r"(a[2]), "r"(a[3]), "r"(db), "n"(HB), "n"(0));
  }
};
template <> struct WgRS<64> {
  template <uint32_t HB>
  static __device__ __forceinline__ void mma(float* d, const uint32_t* a, uint32_t db) {
    asm volatile("{\n.reg .pred p;\n.reg .b64 db;\nsetp.ne.b32 p, %38, 0;\n"
      "mov.b64 db, {%36, %37};\n"
      "wgmma.mma_async.sync.aligned.m64n64k16.f32.bf16.bf16 {"
      "%0, %1, %2, %3, %4, %5, %6, %7, %8, %9, %10, %11, %12, %13, %14, %15, "
      "%16, %17, %18, %19, %20, %21, %22, %23, %24, %25, %26, %27, %28, %29, %30, %31"
      "}, {%32, %33, %34, %35}, db, p, 1, 1, 1;\n}\n"
      : "+f"(d[0]), "+f"(d[1]), "+f"(d[2]), "+f"(d[3]), "+f"(d[4]), "+f"(d[5]), "+f"(d[6]), "+f"(d[7]),
        "+f"(d[8]), "+f"(d[9]), "+f"(d[10]), "+f"(d[11]), "+f"(d[12]), "+f"(d[13]), "+f"(d[14]), "+f"(d[15]),
        "+f"(d[16]), "+f"(d[17]), "+f"(d[18]), "+f"(d[19]), "+f"(d[20]), "+f"(d[21]), "+f"(d[22]), "+f"(d[23]),
        "+f"(d[24]), "+f"(d[25]), "+f"(d[26]), "+f"(d[27]), "+f"(d[28]), "+f"(d[29]), "+f"(d[30]), "+f"(d[31])
      : "r"(a[0]), "r"(a[1]), "r"(a[2]), "r"(a[3]), "r"(db), "n"(HB), "n"(1));
  }
  template <uint32_t HB>
  static __device__ __forceinline__ void set(float* d, const uint32_t* a, uint32_t db) {
    asm volatile("{\n.reg .pred p;\n.reg .b64 db;\nsetp.ne.b32 p, %38, 0;\n"
      "mov.b64 db, {%36, %37};\n"
      "wgmma.mma_async.sync.aligned.m64n64k16.f32.bf16.bf16 {"
      "%0, %1, %2, %3, %4, %5, %6, %7, %8, %9, %10, %11, %12, %13, %14, %15, "
      "%16, %17, %18, %19, %20, %21, %22, %23, %24, %25, %26, %27, %28, %29, %30, %31"
      "}, {%32, %33, %34, %35}, db, p, 1, 1, 1;\n}\n"
      : "=f"(d[0]), "=f"(d[1]), "=f"(d[2]), "=f"(d[3]), "=f"(d[4]), "=f"(d[5]), "=f"(d[6]), "=f"(d[7]),
        "=f"(d[8]), "=f"(d[9]), "=f"(d[10]), "=f"(d[11]), "=f"(d[12]), "=f"(d[13]), "=f"(d[14]), "=f"(d[15]),
        "=f"(d[16]), "=f"(d[17]), "=f"(d[18]), "=f"(d[19]), "=f"(d[20]), "=f"(d[21]), "=f"(d[22]), "=f"(d[23]),
        "=f"(d[24]), "=f"(d[25]), "=f"(d[26]), "=f"(d[27]), "=f"(d[28]), "=f"(d[29]), "=f"(d[30]), "=f"(d[31])
      : "r"(a[0]), "r"(a[1]), "r"(a[2]), "r"(a[3]), "r"(db), "n"(HB), "n"(0));
  }
};
template <> struct WgSST<48> {
  template <uint32_t HA, uint32_t HB>
  static __device__ __forceinline__ void mma(float* d, uint32_t da, uint32_t db, int sc) {
    asm volatile("{\n.reg .pred p;\n.reg .b64 da, db;\nsetp.ne.b32 p, %28, 0;\n"
      "mov.b64 da, {%24, %25};\nmov.b64 db, {%26, %27};\n"
      "wgmma.mma_async.sync.aligned.m64n48k16.f32.bf16.bf16 {"
      "%0, %1, %2, %3, %4, %5, %6, %7, %8, %9, %10, %11, %12, %13, %14, %15, "
      "%16, %17, %18, %19, %20, %21, %22, %23"
      "}, da, db, p, 1, 1, 0, 1;\n}\n"
      : "+f"(d[0]), "+f"(d[1]), "+f"(d[2]), "+f"(d[3]), "+f"(d[4]), "+f"(d[5]), "+f"(d[6]), "+f"(d[7]),
        "+f"(d[8]), "+f"(d[9]), "+f"(d[10]), "+f"(d[11]), "+f"(d[12]), "+f"(d[13]), "+f"(d[14]), "+f"(d[15]),
        "+f"(d[16]), "+f"(d[17]), "+f"(d[18]), "+f"(d[19]), "+f"(d[20]), "+f"(d[21]), "+f"(d[22]), "+f"(d[23])
      : "r"(da), "n"(HA), "r"(db), "n"(HB), "r"(sc));
  }
};
template <> struct WgSST<80> {
  template <uint32_t HA, uint32_t HB>
  static __device__ __forceinline__ void mma(float* d, uint32_t da, uint32_t db, int sc) {
    asm volatile("{\n.reg .pred p;\n.reg .b64 da, db;\nsetp.ne.b32 p, %44, 0;\n"
      "mov.b64 da, {%40, %41};\nmov.b64 db, {%42, %43};\n"
      "wgmma.mma_async.sync.aligned.m64n80k16.f32.bf16.bf16 {"
      "%0, %1, %2, %3, %4, %5, %6, %7, %8, %9, %10, %11, %12, %13, %14, %15, "
      "%16, %17, %18, %19, %20, %21, %22, %23, %24, %25, %26, %27, %28, %29, %30, %31, "
      "%32, %33, %34, %35, %36, %37, %38, %39"
      "}, da, db, p, 1, 1, 0, 1;\n}\n"
      : "+f"(d[0]), "+f"(d[1]), "+f"(d[2]), "+f"(d[3]), "+f"(d[4]), "+f"(d[5]), "+f"(d[6]), "+f"(d[7]),
        "+f"(d[8]), "+f"(d[9]), "+f"(d[10]), "+f"(d[11]), "+f"(d[12]), "+f"(d[13]), "+f"(d[14]), "+f"(d[15]),
        "+f"(d[16]), "+f"(d[17]), "+f"(d[18]), "+f"(d[19]), "+f"(d[20]), "+f"(d[21]), "+f"(d[22]), "+f"(d[23]),
        "+f"(d[24]), "+f"(d[25]), "+f"(d[26]), "+f"(d[27]), "+f"(d[28]), "+f"(d[29]), "+f"(d[30]), "+f"(d[31]),
        "+f"(d[32]), "+f"(d[33]), "+f"(d[34]), "+f"(d[35]), "+f"(d[36]), "+f"(d[37]), "+f"(d[38]), "+f"(d[39])
      : "r"(da), "n"(HA), "r"(db), "n"(HB), "r"(sc));
  }
};
template <> struct WgSST<192> {
  template <uint32_t HA, uint32_t HB>
  static __device__ __forceinline__ void mma(float* d, uint32_t da, uint32_t db, int sc) {
    asm volatile("{\n.reg .pred p;\n.reg .b64 da, db;\nsetp.ne.b32 p, %100, 0;\n"
      "mov.b64 da, {%96, %97};\nmov.b64 db, {%98, %99};\n"
      "wgmma.mma_async.sync.aligned.m64n192k16.f32.bf16.bf16 {"
      "%0, %1, %2, %3, %4, %5, %6, %7, %8, %9, %10, %11, %12, %13, %14, %15, "
      "%16, %17, %18, %19, %20, %21, %22, %23, %24, %25, %26, %27, %28, %29, %30, %31, "
      "%32, %33, %34, %35, %36, %37, %38, %39, %40, %41, %42, %43, %44, %45, %46, %47, "
      "%48, %49, %50, %51, %52, %53, %54, %55, %56, %57, %58, %59, %60, %61, %62, %63, "
      "%64, %65, %66, %67, %68, %69, %70, %71, %72, %73, %74, %75, %76, %77, %78, %79, "
      "%80, %81, %82, %83, %84, %85, %86, %87, %88, %89, %90, %91, %92, %93, %94, %95"
      "}, da, db, p, 1, 1, 0, 1;\n}\n"
      : "+f"(d[0]), "+f"(d[1]), "+f"(d[2]), "+f"(d[3]), "+f"(d[4]), "+f"(d[5]), "+f"(d[6]), "+f"(d[7]),
        "+f"(d[8]), "+f"(d[9]), "+f"(d[10]), "+f"(d[11]), "+f"(d[12]), "+f"(d[13]), "+f"(d[14]), "+f"(d[15]),
        "+f"(d[16]), "+f"(d[17]), "+f"(d[18]), "+f"(d[19]), "+f"(d[20]), "+f"(d[21]), "+f"(d[22]), "+f"(d[23]),
        "+f"(d[24]), "+f"(d[25]), "+f"(d[26]), "+f"(d[27]), "+f"(d[28]), "+f"(d[29]), "+f"(d[30]), "+f"(d[31]),
        "+f"(d[32]), "+f"(d[33]), "+f"(d[34]), "+f"(d[35]), "+f"(d[36]), "+f"(d[37]), "+f"(d[38]), "+f"(d[39]),
        "+f"(d[40]), "+f"(d[41]), "+f"(d[42]), "+f"(d[43]), "+f"(d[44]), "+f"(d[45]), "+f"(d[46]), "+f"(d[47]),
        "+f"(d[48]), "+f"(d[49]), "+f"(d[50]), "+f"(d[51]), "+f"(d[52]), "+f"(d[53]), "+f"(d[54]), "+f"(d[55]),
        "+f"(d[56]), "+f"(d[57]), "+f"(d[58]), "+f"(d[59]), "+f"(d[60]), "+f"(d[61]), "+f"(d[62]), "+f"(d[63]),
        "+f"(d[64]), "+f"(d[65]), "+f"(d[66]), "+f"(d[67]), "+f"(d[68]), "+f"(d[69]), "+f"(d[70]), "+f"(d[71]),
        "+f"(d[72]), "+f"(d[73]), "+f"(d[74]), "+f"(d[75]), "+f"(d[76]), "+f"(d[77]), "+f"(d[78]), "+f"(d[79]),
        "+f"(d[80]), "+f"(d[81]), "+f"(d[82]), "+f"(d[83]), "+f"(d[84]), "+f"(d[85]), "+f"(d[86]), "+f"(d[87]),
        "+f"(d[88]), "+f"(d[89]), "+f"(d[90]), "+f"(d[91]), "+f"(d[92]), "+f"(d[93]), "+f"(d[94]), "+f"(d[95])
      : "r"(da), "n"(HA), "r"(db), "n"(HB), "r"(sc));
  }
};

struct FftConst {
  uint32_t f[2][4], fi[4][4];
  uint32_t ta[2][2], tb[2][2];
};
__device__ __forceinline__ void cis(int m, float scale, float& c, float& s) {
  const float a = (float)m * (-6.283185307179586f * scale);
  c = __cosf(a);
  s = __sinf(a);
}
__device__ __forceinline__ void fft_tables(uint32_t (&v)[12], int tw) {
  const int row = tw >> 2, ch = tw & 3;
#pragma unroll
  for (int i = 0; i < 4; i++) {
    float c[2], s[2], x[2];
#pragma unroll
    for (int e = 0; e < 2; e++) {
      cis((((32 * (8 * ch + 2 * i + e) + 15) * (4 * row - 63) + 2048) & 4095) - 2048, 1.f / 4096, c[e], s[e]);
      float gc, gs;
      cis((((row & 15) * (8 * (ch & 1) + 2 * i + e) + 8) & 15) - 8, 1.f / 16, gc, gs);
      x[e] = (row >> 4) == (ch >> 1) ? gc : (ch >> 1) ? gs : -gs;
    }
    v[i] = pack2(c[0] * 0.125f, c[1] * 0.125f);
    v[4 + i] = pack2(s[0] * 0.125f, s[1] * 0.125f);
    v[8 + i] = pack2(x[0], x[1]);
  }
#pragma unroll
  for (int i = 0; i < 12; i++) asm volatile("" : "+r"(v[i]));
}
__device__ __forceinline__ void fft_tables_store(const uint32_t (&v)[12], uint32_t sb, int tw) {
  const int row = tw >> 2;
  const uint32_t x = ((tw ^ (row >> 1)) & 3) << 4, a = sb + OFF_FT + (16 * (row >> 3) + (row & 7)) * 64 + x;
  sts128(a, v[0], v[1], v[2], v[3]);
  sts128(a + 512, v[4], v[5], v[6], v[7]);
  sts128(sb + OFF_GT + row * 64 + x, v[8], v[9], v[10], v[11]);
}
__device__ __forceinline__ void fft_twiddles(uint32_t (&v)[2], int tw) {
  float a[2], s[2];
#pragma unroll
  for (int i = 0; i < 2; i++) {
    float c;
    cis((2 * (2 * (tw & 3) + i) - 15) * (4 * (tw >> 2) - 63), 1.f / 4096, c, s[i]);
    a[i] = __fdividef(-s[i], 1.f + c);
  }
  v[0] = pack2(a[0], a[1]);
  v[1] = pack2(s[0], s[1]);
  asm volatile("" : "+r"(v[0]), "+r"(v[1]));
}
__device__ __forceinline__ void fft_matrices(FftConst& k, uint32_t sb, int w, int lane) {
  const uint32_t x = (lane >> 1) & 3;
  const uint2 t0 = lds64(sb + OFF_TT + 256 * w + 8 * lane), t1 = lds64(sb + OFF_TT + 256 * w + 8 * (lane ^ 3));
  k.ta[0][0] = t0.x;
  k.tb[0][0] = t0.y;
  k.ta[1][1] = __byte_perm(t1.x, 0, 0x1032);
  k.tb[1][1] = __byte_perm(t1.y, 0, 0x1032);
#pragma unroll
  for (int j = 0; j < 2; j++) {
    k.ta[1 - j][j] = k.ta[j][j] ^ 0x80008000u;
    k.tb[1 - j][j] = k.tb[j][j] ^ 0x80008000u;
    asm volatile("" : "+r"(k.ta[0][j]), "+r"(k.tb[0][j]), "+r"(k.ta[1][j]), "+r"(k.tb[1][j]));
  }
#pragma unroll
  for (int i = 0; i < 2; i++) {
    ldsm4(k.f[i], sb + OFF_FT + (16 * w + (lane & 15)) * 64 + (((2 * i + (lane >> 4)) ^ x) << 4));
    ldsm4t(k.fi[i], sb + OFF_FT + (32 * i + lane) * 64 + ((w ^ x) << 4));
#pragma unroll
    for (int j = 0; j < 4; j++) {
      k.fi[2 + i][j] = (j & 1) ? k.fi[i][j - 1] ^ 0x80008000u : k.fi[i][j + 1];
      asm volatile("" : "+r"(k.fi[2 + i][j]));
    }
  }
}
__device__ __forceinline__ void rot(uint32_t& x, uint32_t& y, uint32_t a, uint32_t b) {
  x = bfma(a, y, x);
  y = bfma(b, x, y);
  x = bfma(a, y, x);
}
__device__ __forceinline__ void twiddle_fwd(uint32_t (&a)[4][4], float* d, const FftConst& k) {
#pragma unroll
  for (int q = 0; q < 4; q++)
#pragma unroll
    for (int j = 0; j < 2; j++) {
      const float* x = d + 8 * q + 4 * j;
      uint32_t re = pack2(x[0], x[1]), im = pack2(x[2], x[3]);
      rot(re, im, k.ta[0][j], k.tb[0][j]);
      a[q & 2][2 * j + (q & 1)] = re;
      a[(q & 2) + 1][2 * j + (q & 1)] = im;
    }
}
__device__ __forceinline__ void g_step(float* d, const uint32_t (&a)[4][4], uint32_t dre, uint32_t dim) {
  WgRS<32>::set<HI_SW64>(d, a[0], dre);
  WgRS<32>::set<HI_SW64>(d + 16, a[2], dre);
  WgRS<32>::mma<HI_SW64>(d, a[1], dim);
  WgRS<32>::mma<HI_SW64>(d + 16, a[3], dim);
  wg_commit();
}

__device__ __forceinline__ void products(uint32_t (&a)[4][4], const float* H, const float* U, int p) {
#pragma unroll
  for (int j = 0; j < 2; j++)
#pragma unroll
    for (int m = 2 * p; m < 2 * p + 2; m++) {
      float pr[2], pi[2];
#pragma unroll
      for (int x = 0; x < 2; x++)
#pragma unroll
        for (int q = 0; q <= m; q++) {
          const int ih = 16 * (q >> 1) + 2 * (q & 1) + 4 * j + x, iu = 16 * ((m - q) >> 1) + 2 * ((m - q) & 1) + 4 * j + x;
          pr[x] = q ? fmaf(H[ih], U[iu], pr[x]) : H[ih] * U[iu];
          pi[x] = q ? fmaf(H[ih], U[iu + 8], pi[x]) : H[ih] * U[iu + 8];
          pr[x] = fmaf(-H[ih + 8], U[iu + 8], pr[x]);
          pi[x] = fmaf(H[ih + 8], U[iu], pi[x]);
        }
      a[m & 2][2 * j + (m & 1)] = pack2(pr[0], pr[1]);
      a[(m & 2) + 1][2 * j + (m & 1)] = pack2(pi[0], pi[1]);
    }
}

__device__ __forceinline__ void conv_channel(const FftConst& k, uint32_t sb, int c, int wg, int w, int lane) {
  const uint32_t cb = sb + off_ch(c), bars = sb + OFF_BAR;
  const uint32_t du = desc_lo(cb, 1024), dg = desc_lo(sb + OFF_GT, 16), dz = desc_lo(cb + U_BYTES, 16);
  float U[32], H[32];
  uint32_t a[4][4], e[4][4];
  const float dv = __uint_as_float(lds32(sb + OFF_D + 4 * c));
  wg_fence();
  WgRS<64>::set<HI_SW32>(H, k.f[0], du + 256);
  WgRS<64>::mma<HI_SW32>(H, k.f[1], du + 256 + 32);
  wg_commit();
  wg_wait<0>();
  pin<32>(H);
  twiddle_fwd(a, H, k);
  mbar_wait(bars + 8 * (B_U + (c < 3 ? c : 3)), 0);
  TSM(w == 0 && c < 3, 7 + wg);
  wg_fence();
  WgRS<64>::set<HI_SW32>(U, k.f[0], du);
  WgRS<64>::mma<HI_SW32>(U, k.f[1], du + 32);
  wg_commit();
  g_step(H, a, dg, dg + 64);
  wg_wait<1>();
  pin<32>(U);
  twiddle_fwd(e, U, k);
  wg_fence();
  g_step(U, e, dg, dg + 64);
  wg_wait<0>();
  pin<32>(U);
  pin<32>(H);
#pragma unroll
  for (int j = 0; j < 4; j++) H[4 * (j >> 1) + (j & 1)] += dv;
  float V[32];
#pragma unroll
  for (int p = 0; p < 2; p++) {
    products(a, H, U, p);
    wg_fence();
    WgRS<32>::set<HI_SW64>(V + 16 * p, a[2 * p], dg + 64);
    WgRS<32>::mma<HI_SW64>(V + 16 * p, a[2 * p + 1], dg);
    wg_commit();
  }
  const uint32_t za = cb + U_BYTES + (8 * w + (lane & 7)) * 128 + (((lane >> 3) ^ (lane & 7)) << 4);
  const uint32_t ya = cb + (lane >> 4) * 1024 + (8 * w + (lane & 7)) * 32 + ((((lane >> 3) ^ (lane >> 2)) & 1) << 4);
  wg_sync(1 + wg);
#pragma unroll
  for (int p = 0; p < 2; p++) {
    if (p == 0) wg_wait<1>();
    else wg_wait<0>();
    pin<16>(V + 16 * p);
#pragma unroll
    for (int i = 0; i < 4; i++) {
      const int j = i & 1;
      const float* x = V + 16 * p + 4 * j + (i & 2);
      e[p][i] = pack2(x[8], x[9]);
      e[2 + p][i] = pack2(x[0], x[1]);
      rot(e[p][i], e[2 + p][i], k.ta[1][j], k.tb[1][j]);
    }
    stsm4(za ^ (64 * p), e[p]);
    stsm4((za ^ (64 * p)) + 4096, e[2 + p]);
  }
  fence_async_smem();
  wg_sync(1 + wg);
  wg_fence();
  WgRS<64>::set<HI_SW128>(H, k.fi[0], dz);
#pragma unroll
  for (int ks = 1; ks < 4; ks++) WgRS<64>::mma<HI_SW128>(H, k.fi[ks], dz + 128 * ks);
  wg_commit();
  wg_wait<0>();
  pin<32>(H);
  if (lane == 0) mbar_arrive(bars + 8 * B_CVD);
  TSIF(w == 0, 88 + c);
#pragma unroll
  for (int j = 0; j < 8; j++)
    a[j >> 2][j & 3] = j < 2 ? pack2(H[4 * j], H[4 * j + 1]) : pack2(H[4 * j] + H[4 * j - 6], H[4 * j + 1] + H[4 * j - 5]);
  stsm4(ya, a[0]);
  stsm4(ya + 2048, a[1]);
  fence_async_smem();
  __syncwarp();
}

__device__ __forceinline__ void prep_slab(uint4* res, const uint2* sw, uint32_t sb, int slab, int w, int lane) {
  const int t = lane & 3, tp = (lane & 7) >> 1, pos = 8 * tp + 2 * (((lane >> 3) + tp) & 3) + (lane & 1);
  const uint32_t base = sb + OFF_KVS + slab * KVS_BYTES + pos * 128;
  uint32_t kk[2][4][4], vv[2][4];
  mbar_wait(sb + OFF_BAR + 8 * (B_KV + slab), 0);
#pragma unroll
  for (int h = 0; h < 2; h++) {
#pragma unroll
    for (int j = 0; j < 4; j++) {
      const uint32_t a = base + 128 * j;
      ldsm4t(kk[h][j], a + (((w + 4 * h) ^ ((a >> 7) & 7)) << 4));
    }
    const uint32_t a = base + KVS_V;
    ldsm4t(vv[h], a + (((w + 4 * h) ^ ((a >> 7) & 7)) << 4));
  }
#pragma unroll
  for (int h = 0; h < 2; h++) {
    uint32_t (&k)[4][4] = kk[h];
    uint32_t (&v)[4] = vv[h];
    const uint32_t w0 = __byte_perm(sw[h].x, 0, 0x1010), w1 = __byte_perm(sw[h].x, 0, 0x3232);
    const uint32_t w2 = __byte_perm(sw[h].y, 0, 0x1010), w3 = __byte_perm(sw[h].y, 0, 0x3232);
#pragma unroll
    for (int m = 0; m < 4; m++)
      v[m] = bmul(badd(badd(badd(bmul(k[0][m], w3), bmul(k[1][m], w2)), bmul(k[2][m], w1)), bmul(k[3][m], w0)), v[m]);
    uint32_t a[4];
#pragma unroll
    for (int m = 0; m < 4; m++) a[m] = (t & 1) ? v[(m + 3) & 3] : v[m];
    res[h] = (t & 2) ? make_uint4(a[2], a[3], a[0], a[1]) : make_uint4(a[0], a[1], a[2], a[3]);
  }
}

__device__ __forceinline__ void prep_gate(const Params& p, uint32_t sb, int b, int w, int lane) {
  uint2 gw[5], x[4][5];
#pragma unroll
  for (int j = 0; j < 5; j++) gw[j] = ldg64(reinterpret_cast<const uint2*>(p.gate_w) + lane + 32 * j);
#pragma unroll
  for (int i = 0; i < 4; i++)
#pragma unroll
    for (int j = 0; j < 5; j++)
      x[i][j] = ldg64(reinterpret_cast<const uint2*>(p.q) + (16 * b + 4 * w + i) * (DIM / 4) + lane + 32 * j);
  float s[4];
#pragma unroll
  for (int i = 0; i < 4; i++) {
    s[i] = 0.f;
#pragma unroll
    for (int j = 0; j < 5; j++) {
      const uint32_t m0 = bmul(x[i][j].x, gw[j].x), m1 = bmul(x[i][j].y, gw[j].y);
      s[i] += (bf_lo(m0) + bf_hi(m0)) + (bf_lo(m1) + bf_hi(m1));
    }
  }
  const bool h = lane & 16, q = lane & 8;
  const float a = (h ? s[2] : s[0]) + __shfl_xor_sync(0xffffffffu, h ? s[0] : s[2], 16);
  const float c = (h ? s[3] : s[1]) + __shfl_xor_sync(0xffffffffu, h ? s[1] : s[3], 16);
  float z = (q ? c : a) + __shfl_xor_sync(0xffffffffu, q ? a : c, 8);
#pragma unroll
  for (int o = 4; o > 0; o >>= 1) z += __shfl_xor_sync(0xffffffffu, z, o);
  z = bf_lo(pack2(z, 0.f));
  z = bf_lo(pack2(__fdividef(1.f, 1.f + __expf(-z)), 0.f));
  mbar_wait(sb + OFF_BAR + 8 * B_S3, 0);
  if ((lane & 7) == 0) asm volatile("st.shared.f32 [%0], %1;" ::"r"(sb + OFF_GATE + 64 * (b & 7) + 16 * w + (lane >> 1)), "f"(z) : "memory");
  fence_async_smem();
}

__device__ __forceinline__ uint32_t bmax(uint32_t a, uint32_t b) {
  uint32_t d;
  asm("max.bf16x2 %0, %1, %2;" : "=r"(d) : "r"(a), "r"(b));
  return d;
}
__device__ __forceinline__ void softmax_two(const float (&l)[2][2], uint32_t& p0, uint32_t& p1) {
  constexpr float kScale = 0.22360679774997896f, kLog2e = 1.4426950408889634f;
  const uint32_t r0 = pack2(l[0][0], l[1][0]), r1 = pack2(l[0][1], l[1][1]);
  const uint32_t x0 = pack2(bf_lo(r0) * kScale, bf_hi(r0) * kScale), x1 = pack2(bf_lo(r1) * kScale, bf_hi(r1) * kScale);
  uint32_t m = bmax(x0, x1);
  m = bmax(m, __shfl_xor_sync(0xffffffffu, m, 1));
  m = bmax(m, __shfl_xor_sync(0xffffffffu, m, 2));
  const float m0 = bf_lo(m) * kLog2e, m1 = bf_hi(m) * kLog2e;
  p0 = pack2(ex2(bf_lo(x0) * kLog2e - m0), ex2(bf_lo(x1) * kLog2e - m0));
  p1 = pack2(ex2(bf_hi(x0) * kLog2e - m1), ex2(bf_hi(x1) * kLog2e - m1));
}

__device__ __forceinline__ void halo_read(uint32_t (&kpv)[10], uint32_t (&vpv)[10], uint32_t (&tg)[7], const uint4* hp) {
#pragma unroll
  for (int j = 0; j < 7; j++) {
    uint32_t x0, x1, x2;
    asm volatile("ld.relaxed.gpu.global.v4.u32 {%0, %1, %2, %3}, [%4];"
                 : "=r"(x0), "=r"(x1), "=r"(x2), "=r"(tg[j]) : "l"(hp + 32 * j) : "memory");
    if (j < 4) kpv[3 * j] = x0; else vpv[3 * j - 10] = x0;
    if (j < 3) kpv[3 * j + 1] = x1; else vpv[3 * j - 9] = x1;
    if (j < 3) kpv[3 * j + 2] = x2; else if (j < 6) vpv[3 * j - 8] = x2;
  }
}

template <int ROT>
__device__ __forceinline__ void pack_qkv(const float* acc, uint32_t (&qlo)[10], uint32_t (&qhi)[10], uint32_t (&klo)[10],
                                         uint32_t (&khi)[10], uint32_t (&vlo)[10], uint32_t (&vhi)[10]) {
#pragma unroll
  for (int j = 0; j < 10; j++) {
    const int x = (j + ROT) % 10, tq = x < 8 ? x : 16 + x, tk = x < 8 ? 8 + x : 18 + x, tv = x < 8 ? 16 + x : 20 + x;
    khi[j] = pack2(acc[4 * tk + 2], acc[4 * tk + 3]);
    vhi[j] = movm(pack2(acc[4 * tv + 2], acc[4 * tv + 3]));
    qlo[j] = pack2(acc[4 * tq], acc[4 * tq + 1]);
    qhi[j] = pack2(acc[4 * tq + 2], acc[4 * tq + 3]);
    klo[j] = pack2(acc[4 * tk], acc[4 * tk + 1]);
    vlo[j] = pack2(acc[4 * tv], acc[4 * tv + 1]);
    asm volatile("" : "+r"(khi[j]), "+r"(qlo[j]), "+r"(qhi[j]), "+r"(klo[j]), "+r"(vlo[j]));
  }
}

template <int ROT> __device__ __forceinline__ void halo_send(const float* acc, uint4* ho, uint32_t tag) {
#pragma unroll
  for (int j = 0; j < 7; j++) {
    uint32_t x[3];
#pragma unroll
    for (int e = 0; e < 3; e++) {
      const int i = 3 * j + e, y = (i % 10 + ROT) % 10, tk = y < 8 ? 8 + y : 18 + y, tv = y < 8 ? 16 + y : 20 + y;
      x[e] = i < 10 ? pack2(acc[4 * tk + 2], acc[4 * tk + 3]) : i < 20 ? movm(pack2(acc[4 * tv + 2], acc[4 * tv + 3])) : 0u;
    }
    asm volatile("st.relaxed.gpu.global.v4.u32 [%0], {%1, %2, %3, %4};" ::"l"(ho + 32 * j), "r"(x[0]), "r"(x[1]), "r"(x[2]), "r"(tag) : "memory");
  }
}

__device__ __forceinline__ void attention(float* acc, uint32_t sb, int b, int par, int w, int lane, uint32_t tag, FftConst& fc) {
  const int g = lane >> 2, t = lane & 3;
  uint32_t klo[10], khi[10], vlo[10], vhi[10], qlo[10], qhi[10], kpv[10], vpv[10];
  if (w == 3 && b < NCTA - 8) {
    uint4* ho = g_halo + (b * 2 + par) * 224 + lane;
    if (tail_first(b & 7)) halo_send<8>(acc, ho, tag);
    else halo_send<0>(acc, ho, tag);
    TSIF(par == 0, 76);
    pin<120>(acc);
  }
  if (tail_first(b & 7)) pack_qkv<8>(acc, qlo, qhi, klo, khi, vlo, vhi);
  else pack_qkv<0>(acc, qlo, qhi, klo, khi, vlo, vhi);
  const uint32_t xa = sb + OFF_KVX + (par * 3) * 2560 + lane * 16;
  if (w < 3) {
    sts128(xa + w * 2560, khi[0], khi[1], khi[2], khi[3]);
    sts128(xa + w * 2560 + 512, khi[4], khi[5], khi[6], khi[7]);
    sts128(xa + w * 2560 + 1024, khi[8], khi[9], vhi[0], vhi[1]);
    sts128(xa + w * 2560 + 1536, vhi[2], vhi[3], vhi[4], vhi[5]);
    sts128(xa + w * 2560 + 2048, vhi[6], vhi[7], vhi[8], vhi[9]);
  }
  TSIF(par == 0 && w == 1, 64);
#pragma unroll
  for (int j = 0; j < 10; j++) vlo[j] = movm(vlo[j]);
  const bool far0 = 2 * t > g, far1 = 2 * t + 1 > g;
  const uint32_t mfar = (far0 ? 0x0000FFFFu : 0u) | (far1 ? 0xFFFF0000u : 0u);
  float slo[4][2], lg[2][2];
  uint32_t phi[4], plo[4], qml[4], qmh[4];
#pragma unroll
  for (int h = 0; h < 4; h++) {
    const int f = h == 0 ? 0 : h == 1 ? 3 : h == 2 ? 5 : 8, hf = h < 2 ? 2 : 7;
    const bool mine = (h & 1) ? t >= 2 : t < 2;
    qml[h] = mine ? qlo[hf] : 0u;
    qmh[h] = mine ? qhi[hf] : 0u;
    float a[4] = {0.f, 0.f, 0.f, 0.f}, c[4] = {0.f, 0.f, 0.f, 0.f};
    mma16816(a, qlo[f], qhi[f], qlo[f + 1], qhi[f + 1], klo[f], klo[f + 1]);
    mma16816(c, qlo[f], qhi[f], qlo[f + 1], qhi[f + 1], khi[f], khi[f + 1]);
    mma1688(a, qml[h], qmh[h], klo[hf]);
    mma1688(c, qml[h], qmh[h], khi[hf]);
    slo[h][0] = a[0];
    slo[h][1] = a[1];
    lg[h & 1][0] = far0 ? a[2] : c[2];
    lg[h & 1][1] = far1 ? a[3] : c[3];
    if (h & 1) softmax_two(lg, phi[h - 1], phi[h]);
  }
  TSIF(par == 0 && w == 1, 65);
  wg_sync(1 + par);
  TSIF(par == 0 && w == 1, 66);
  const bool nohist = (w == 0) && (b < 8);
  const uint4* hp = g_halo + ((b - 8) * 2 + par) * 224 + lane;
  uint32_t tg[7];
  if (w > 0) {
    const uint4 v0 = lds128(xa + (w - 1) * 2560), v1 = lds128(xa + (w - 1) * 2560 + 512), v2 = lds128(xa + (w - 1) * 2560 + 1024);
    const uint4 v3 = lds128(xa + (w - 1) * 2560 + 1536), v4 = lds128(xa + (w - 1) * 2560 + 2048);
    kpv[0] = v0.x; kpv[1] = v0.y; kpv[2] = v0.z; kpv[3] = v0.w; kpv[4] = v1.x; kpv[5] = v1.y; kpv[6] = v1.z; kpv[7] = v1.w;
    kpv[8] = v2.x; kpv[9] = v2.y; vpv[0] = v2.z; vpv[1] = v2.w; vpv[2] = v3.x; vpv[3] = v3.y; vpv[4] = v3.z; vpv[5] = v3.w;
    vpv[6] = v4.x; vpv[7] = v4.y; vpv[8] = v4.z; vpv[9] = v4.w;
  } else if (nohist) {
#pragma unroll
    for (int j = 0; j < 10; j++) kpv[j] = vpv[j] = 0u;
  } else {
    TSIF(par == 0, 77);
    halo_read(kpv, vpv, tg, hp);
  }
  if (w == 0 && !nohist) {
    int spins = 0;
    while (true) {
      bool ok = true;
#pragma unroll
      for (int j = 0; j < 7; j++) ok = ok && tg[j] == tag;
      if (__all_sync(0xffffffffu, ok) || ++spins > SPIN_LIMIT) break;
      halo_read(kpv, vpv, tg, hp);
    }
    TSIF(par == 0, 79);
  }
#pragma unroll
  for (int h = 0; h < 4; h++) {
    const int f = h == 0 ? 0 : h == 1 ? 3 : h == 2 ? 5 : 8, hf = h < 2 ? 2 : 7;
    float a[4] = {0.f, 0.f, 0.f, 0.f};
    mma16816(a, qlo[f], qhi[f], qlo[f + 1], qhi[f + 1], kpv[f], kpv[f + 1]);
    mma1688(a, qml[h], qmh[h], kpv[hf]);
    const float ninf = __int_as_float(0xff800000);
    lg[h & 1][0] = far0 ? (nohist ? ninf : a[0]) : slo[h][0];
    lg[h & 1][1] = far1 ? (nohist ? ninf : a[1]) : slo[h][1];
    if (h & 1) softmax_two(lg, plo[h - 1], plo[h]);
  }
  TSIF(par == 0 && w <= 1, 67 + w);
  mbar_wait(sb + OFF_BAR + 8 * B_HA, 0);
  fft_matrices(fc, sb, w, lane);
  uint32_t ov[20];
#pragma unroll
  for (int hp = 0; hp < 2; hp++) {
    const int hf = hp ? 7 : 2;
    float sh[4] = {0.f, 0.f, 0.f, 0.f}, i0 = 0.f, i1 = 0.f;
#pragma unroll
    for (int e = 0; e < 2; e++) {
      const int h = 2 * hp + e, f = h == 0 ? 0 : h == 1 ? 3 : h == 2 ? 5 : 8;
      const uint32_t a0 = plo[h] & mfar, a2 = plo[h] & ~mfar, a3 = phi[h] & mfar, c1 = phi[h] & ~mfar;
      float sum[4] = {0.f, 0.f, 0.f, 0.f};
      mma1688(sum, plo[h], phi[h], 0x3F803F80u);
      const float r0 = rcp(sum[0]), r1 = rcp(sum[2]);
#pragma unroll
      for (int j = f; j < f + 2; j++) {
        float o[4] = {0.f, 0.f, 0.f, 0.f};
        mma16816(o, a0, 0u, a2, a3, vpv[j], vlo[j]);
        mma1688(o, 0u, c1, vhi[j]);
        ov[2 * j] = pack2(o[0] * r0, o[1] * r0);
        ov[2 * j + 1] = pack2(o[2] * r1, o[3] * r1);
      }
      const bool mine = e ? g >= 4 : g < 4;
      mma16816(sh, a0, 0u, a2, a3, mine ? vpv[hf] : 0u, mine ? vlo[hf] : 0u);
      mma1688(sh, 0u, c1, mine ? vhi[hf] : 0u);
      if (e == 0 || t >= 2) {
        i0 = r0;
        i1 = r1;
      }
    }
    ov[2 * hf] = pack2(sh[0] * i0, sh[1] * i0);
    ov[2 * hf + 1] = pack2(sh[2] * i1, sh[3] * i1);
  }
  TS(32 + 4 * par + w);
  mbar_wait(sb + OFF_BAR + 8 * B_P1, 0);
  const uint32_t oa = sb + OFF_OA + (lane >> 4) * 2048 + (32 * w + 2 * (lane & 15) + par) * 16;
#pragma unroll
  for (int j = 0; j < 5; j++) stsm4(oa + 4096 * j, ov + 4 * j);
  TSIF(par == 0 && w == 0, 120);
  fence_async_smem();
  TSIF(par == 0 && w == 0, 121);
  __syncwarp();
  if (lane == 0) mbar_arrive(sb + OFF_BAR + 8 * B_ATTN);
  TSM(w == 0 || w == 2, 122 + par + (w == 2 ? 3 : 0));
}

struct Maps {
  CUtensorMap x, wm, wt, k, v, y, wo, qm, qt, om, ot, yl, ol, wh;
};

__device__ __forceinline__ void load_stage(uint32_t sb, int kb, int b, const Maps& m) {
  const uint32_t st = sb + (kb & 3) * STAGE_BYTES, bar = sb + OFF_BAR + 8 * (B_FULL1 + (kb & 3));
  const int r = b >> 3, hg = b & 7, slab = kb - KV_KB;
  const bool kv = slab >= 0 && slab < 5;
  const uint32_t kbar = sb + OFF_BAR + 8 * (B_KV + slab), dst = sb + OFF_KVS + slab * KVS_BYTES;
  mbar_expect_tx(bar, STAGE_BYTES);
  if (kv) mbar_expect_tx(kbar, KVS_BYTES);
  tma_3d(st, &m.x, 64 * kb, 64 * r, 0, bar);
  tma_3d(st + ST_W, &m.wm, 80 * hg + (tail_first(hg) ? 16 : 0), 64 * kb, 0, bar);
  tma_3d(st + ST_WT, &m.wt, 80 * hg + (tail_first(hg) ? 0 : 64), 64 * kb, 0, bar);
  if (kv) tma_3d(dst, &m.k, 0, 32 * (b >> 1) - 3, 2 * slab + (b & 1), kbar);
  if (kv) tma_3d(dst + KVS_V, &m.v, 0, 32 * (b >> 1), 2 * slab + (b & 1), kbar);
}

__global__ void __launch_bounds__(NTHR, 1) fused_kernel(const __grid_constant__ Maps m, const Params p) {
  extern __shared__ __align__(1024) uint8_t smem[];
  const uint32_t sb = (uint32_t)__cvta_generic_to_shared(smem);
  const uint32_t bars = sb + OFF_BAR;
  const int tid = threadIdx.x, lane = tid & 31;
  int b = blockIdx.x;
  b = (((b & 63) >> 3) * 2 + (b & 1)) * 8 + (((b < 64 ? 0x6521 : 0x7430) >> (4 * ((b >> 1) & 3))) & 7);
  const int r = b >> 3, hg = b & 7;

  if (tid == T_ISSUE) {
    TSM(true, 0);
#pragma unroll
    for (int i = 0; i < 4; i++) mbar_init(bars + 8 * (B_F0 + i), 1);
    fence_async_smem();
#pragma unroll
    for (int i = 0; i < 4; i++) {
      mbar_expect_tx(bars + 8 * (B_F0 + i), (i ? 0 : ST_W) + 6144);
      if (i == 0) tma_3d(sb, &m.x, 0, 64 * r, 0, bars + 8 * B_F0);
      tma_3d(sb + ST_W + 6144 * i, &m.wh, 80 * hg + (tail_first(hg) ? 16 : 0), 16 * i, 0, bars + 8 * (B_F0 + i));
    }
#pragma unroll
    for (int i = 0; i < 4; i++) mbar_init(bars + 8 * (B_FULL1 + i), 1);
    fence_async_smem();
    mbar_expect_tx(bars + 8 * B_FULL1, STAGE_BYTES - ST_WT);
    tma_3d(sb + ST_WT, &m.wt, 80 * hg + (tail_first(hg) ? 0 : 64), 0, 0, bars + 8 * B_FULL1);
    load_stage(sb, 1, b, m);
  } else if (tid == T_INIT) {
#pragma unroll
    for (int i = 0; i < B_F0; i++) mbar_init(bars + 8 * i, i < B_GATE ? 8 : i < B_CVD ? 4 : i == B_CVD ? 20 : 1);
    fence_async_smem();
  }
  const int warp = __shfl_sync(0xffffffffu, tid >> 5, 0), wg = warp >> 2, w = warp & 3;
  __syncthreads();

  if (wg == 3) {
    asm volatile("setmaxnreg.dec.sync.aligned.u32 56;");
    if (w == 0) {
      if (lane == 0) {
#pragma unroll 1
        for (int kb = 2; kb < 10; kb++) {
          if (kb >= 4) mbar_wait(bars + 8 * (kb == 7 ? B_E3 : B_EMPTY1 + (kb & 3)), (kb >> 3) & 1);
          TSIF(kb >= 4, 44 + kb);
          load_stage(sb, kb, b, m);
          TSIF(kb == 3, 60);
          if (kb == 9) mbar_arrive(bars + 8 * B_LAST);
        }
        mbar_wait(bars + 8 * B_WOP, 0);
        mbar_wait(bars + 8 * B_EPOCH, 0);
        flag_wait(g_cnt + C_W + 32 * hg, (lds32(sb + OFF_EPOCH) + 1) * 16);
        TS(30);
#pragma unroll 1
        for (int j = 0; j < 8; j++) {
          if (j >= 6) mbar_wait(bars + 8 * (B_EMPTY2 + j - 6), 0);
          if (j == 4) mbar_wait(bars + 8 * B_ORB, 0);
          TSIF(j >= 6, 100 + j);
          mbar_expect_tx(bars + 8 * (B_FULL2 + j), j == 0 ? WO_BYTES : j == 5 ? O_BYTES + WO_BYTES + 512 : O_BYTES + WO_BYTES);
          bulk_load(sb + off_w(j), g_WO + (hg * 8 + step_src(hg, j)) * 800, WO_BYTES, bars + 8 * (B_FULL2 + j));
        }
        mbar_wait(bars + 8 * (B_EMPTY2 + 3), 0);
        mbar_expect_tx(bars + 8 * B_QF, O_BYTES);
        tma_2d(sb + OFF_QS, &m.qm, 80 * hg, 128 * r, bars + 8 * B_QF);
        tma_2d(sb + OFF_QT, &m.qt, 80 * hg + 64, 128 * r, bars + 8 * B_QF);
      }
    } else if (w == 1) {
      unsigned epoch = 0;
      if (lane == 0) {
        epoch = atomicAdd(g_cnt + C_LAUNCH, 1u) / NCTA;
        asm volatile("st.shared.u32 [%0], %1;" ::"r"(sb + OFF_EPOCH), "r"(epoch) : "memory");
        mbar_arrive(bars + 8 * B_EPOCH);
        mbar_wait(bars + 8 * B_KVD, 0);
        mbar_expect_tx(bars + 8 * B_HB, 5 * 4096);
#pragma unroll 1
        for (int c = 0; c < 5; c++) {
          if (c == 3) mbar_wait(bars + 8 * B_S3, 0);
          bulk_load(sb + off_ch(c) + U_BYTES, p.ssm_k + (5 * b + c) * SEQ, 4096, bars + 8 * B_HB);
        }
#pragma unroll
        for (int c = 0; c < 4; c++) mbar_expect_tx(bars + 8 * (B_U + c), c < 3 ? U_BYTES : 2 * U_BYTES);
        const uint4* usrc = g_U + 5 * b * U_PITCH;
        mbar_wait(bars + 8 * B_USIG, 0);
        flag_wait(g_cnt + C_PREP + 32 * (b & 15), (epoch + 1) * NCTA);
        TS(23);
#pragma unroll
        for (int c = 0; c < 5; c++) {
          if (c == 3) mbar_wait(bars + 8 * (B_U + 2), 0);
          bulk_load(sb + off_ch(c), usrc + c * U_PITCH, U_BYTES, bars + 8 * (B_U + (c < 3 ? c : 3)));
          TSIF(c == 0 || c == 4, 116 + (c >> 2));
        }
      }
      epoch = __shfl_sync(0xffffffffu, epoch, 0);
      if (lane < 8) {
        const int src = (b & ~7) | step_src(hg, lane);
        mbar_wait(bars + 8 * B_ATTN, 0);
        TS(20);
        bool seen = false;
#pragma unroll 1
        for (int spins = 0; spins < SPIN_LIMIT; spins++) {
          const bool now = !seen && (int)(flag_read(g_cnt + C_O + 32 * src) - (epoch + 1)) >= 0;
          if (now && lane >= 1 && lane < 4) bulk_load(sb + off_o(lane), g_O + src * 1280, O_BYTES, bars + 8 * (B_FULL2 + lane));
          seen = seen || now;
          if (__all_sync(0xff, seen)) break;
        }
        TS(21);
        if (lane == 5) bulk_load(sb + OFF_GATE, g_gate + 128 * r, 512, bars + 8 * (B_FULL2 + 5));
#pragma unroll 1
        for (int j = 4; j < 8; j++) {
          if (lane == j) {
            mbar_wait(bars + 8 * (j < 6 ? B_C34 : B_EMPTY2 + j - 6), 0);
            bulk_load(sb + off_o(j), g_O + src * 1280, O_BYTES, bars + 8 * (B_FULL2 + j));
          }
          __syncwarp(0xff);
        }
        TS(22);
      }
    } else if (w == 2) {
      mbar_wait(bars + 8 * B_PREP, 0);
      flag_signal(g_cnt + C_PREP, 16, lane);
      TS(25);
      if (lane == 0) {
        mbar_arrive(bars + 8 * B_USIG);
        mbar_expect_tx(bars + 8 * B_ORB, O_BYTES / 4 + 64);
        mbar_wait(bars + 8 * B_GATE, 0);
        publish(g_gate + 16 * b, sb + OFF_GATE + 64 * hg, 64);
        bulk_load(sb + OFF_GATE + 64 * hg, g_gate + 16 * b, 64, bars + 8 * B_ORB);
        mbar_wait(bars + 8 * B_ATTN, 0);
        publish(g_O + b * 1280, sb + OFF_OA, O_BYTES);
        tma_2d(sb + OFF_KVX + 10240, &m.ol, 48, b * 160, bars + 8 * B_ORB);
        TS(74);
        mbar_wait(bars + 8 * B_ORB, 0);
        flag_bump(g_cnt + C_O + 32 * b);
        TS(26);
      }
    } else {
      if (lane == 0) {
        uint4* dst = g_WO + (hg * 8 + (r >> 1)) * 800 + (r & 1) * 80;
        mbar_wait(bars + 8 * B_S3, 0);
        asm volatile("cp.async.bulk.prefetch.L2.global [%0], 6400;" ::"l"(p.wo + b * 3200) : "memory");
        mbar_wait(bars + 8 * B_P1, 0);
        mbar_wait(bars + 8 * WB_TRIG, 0);
        mbar_expect_tx(bars + 8 * B_WST, WO_BYTES / 2);
        tma_3d(sb + OFF_WA, &m.wo, 0, 40 * r, 5 * hg, bars + 8 * B_WST);
        mbar_wait(bars + 8 * B_WST, 0);
#pragma unroll 1
        for (int n = 0; n < 5; n++) bulk_store(dst + 160 * n, sb + OFF_WA + 1280 * n, 1280);
        bulk_wait_read();
        mbar_expect_tx(bars + 8 * B_WST, WO_BYTES / 2);
#pragma unroll 1
        for (int n = 0; n < 5; n++) bulk_load(sb + OFF_WA + 1280 * n, dst + 160 * n, 1280, bars + 8 * B_WST);
        mbar_wait(bars + 8 * B_WST, 1);
        flag_bump(g_cnt + C_W + 32 * hg);
        mbar_arrive(bars + 8 * B_WOP);
        TS(71);
        mbar_expect_tx(bars + 8 * B_C34, 3 * (U_BYTES / 4));
        mbar_expect_tx(bars + 8 * B_YRB, 2 * (U_BYTES / 4));
#pragma unroll 1
        for (int c = 0; c < 5; c++) {
          mbar_wait(bars + 8 * (B_YST + c), 0);
          publish(g_U + (5 * b + c) * U_PITCH, sb + off_ch(c), U_BYTES);
          tma_2d(sb + off_ch(c), &m.yl, 48, (5 * b + c) * (U_PITCH / 8), bars + 8 * (c < 3 ? B_C34 : B_YRB));
        }
        TS(75);
        mbar_wait(bars + 8 * B_C34, 0);
        mbar_wait(bars + 8 * B_YRB, 0);
        flag_bump(g_cnt + C_Y + 32 * (b >> 4));
        TS(27);
        mbar_expect_tx(bars + 8 * B_YFULL, 20480);
        flag_wait(g_cnt + C_Y + 32 * hg, (lds32(sb + OFF_EPOCH) + 1) * 16);
        TS(24);
        tma_2d(sb + OFF_YT, &m.y, 128 * r, 80 * hg, bars + 8 * B_YFULL);
        tma_2d(sb + OFF_YT + 10240, &m.y, 128 * r + 64, 80 * hg, bars + 8 * B_YFULL);
      }
    }
  } else {
    asm volatile("setmaxnreg.inc.sync.aligned.u32 152;");
    FftConst fc;
    if (wg < 2) {
      float acc[120];
#pragma unroll
      for (int i = 0; i < 120; i++) acc[i] = 0.f;
      const uint32_t da = desc_lo(sb + wg * 8192, 16), db = desc_lo(sb + ST_W, 8192), dc = desc_lo(sb + ST_WT, 2048);
#pragma unroll
      for (int k = 0; k < 4; k++) {
        mbar_wait(bars + 8 * (B_F0 + k), 0);
        TSIF(w == 0 && wg == 0 && k == 0, 1);
        wg_fence();
        WgSST<192>::mma<HI_SW128, HI_SW128>(acc, da + 2 * k, desc_lo(sb + ST_W, 2048) + 384 * k, 1);
        wg_commit();
      }
      mbar_wait(bars + 8 * B_FULL1, 0);
      wg_fence();
#pragma unroll
      for (int k = 0; k < 4; k++) WgSST<48>::mma<HI_SW128, HI_SW32>(acc + 96, da + 2 * k, dc + 32 * k, 1);
      wg_commit();
#pragma unroll 1
      for (int kb = 1; kb < 10; kb++) {
        mbar_wait(bars + 8 * (B_FULL1 + (kb & 3)), (kb >> 2) & 1);
        const uint32_t so = (kb & 3) * (STAGE_BYTES >> 4);
        wg_fence();
#pragma unroll
        for (int k = 0; k < 4; k++) {
          WgSST<192>::mma<HI_SW128, HI_SW128>(acc, da + so + 2 * k, db + so + 128 * k, 1);
          WgSST<48>::mma<HI_SW128, HI_SW32>(acc + 96, da + so + 2 * k, dc + so + 32 * k, 1);
        }
        wg_commit();
        wg_wait<1>();
        if (lane == 0) mbar_arrive(bars + 8 * (kb == 4 ? B_E3 : B_EMPTY1 + ((kb - 1) & 3)));
      }
      mbar_wait(bars + 8 * B_EPOCH, 0);
      const uint32_t tag = lds32(sb + OFF_EPOCH) + 1;
      mbar_wait(bars + 8 * B_S3, 0);
      wg_wait<0>();
      pin<120>(acc);
      if (lane == 0) mbar_arrive(bars + 8 * B_P1);
      TSM(w == 0, 3 + wg);
      attention(acc, sb, b, wg, w, lane, tag, fc);
    } else {
      const int tw = tid & 127, chl = 64 * (b & 1) + 8 * w + (lane >> 2);
      uint4* up = g_U + chl * U_PITCH + ((4 * (b >> 1) + (lane & 3)) ^ ((b >> 2) & 1));
      uint2 sw[10];
      uint32_t dv = 0;
      if (lane < 5) dv = __ldg(reinterpret_cast<const unsigned short*>(p.ssm_D) + 5 * b + lane);
#pragma unroll
      for (int i = 0; i < 10; i++) sw[i] = ldg64(reinterpret_cast<const uint2*>(p.shift_k) + chl + 128 * (i >> 1) + 32 * (i & 1));
      uint32_t tab[12];
      uint32_t tt[2];
      fft_tables(tab, tw);
      fft_twiddles(tt, tw);
      uint4 res[10];
#pragma unroll
      for (int i = 0; i < 10; i++) res[i] = make_uint4(0, 0, 0, 0);
#pragma unroll 1
      for (int slab = 0; slab < 5; slab++) {
#pragma unroll
        for (int i = 0; i < 8; i++) res[i] = res[i + 2];
        prep_slab(res + 8, sw, sb, slab, w, lane);
        TSIF(w == 0, 99 + 4 * slab);
#pragma unroll
        for (int i = 0; i < 8; i++) sw[i] = sw[i + 2];
      }
      TSIF(w == 0, 28);
      __syncwarp();
      if (lane == 0) mbar_arrive(bars + 8 * B_KVD + ((res[8].x ^ res[9].x) & p.zero));
      mbar_wait(bars + 8 * B_KVD, 0);
      fft_tables_store(tab, sb, tw);
      mbar_wait(bars + 8 * B_LAST, 0);
#pragma unroll
      for (int i = 0; i < 10; i++) up[(128 * (i >> 1) + 32 * (i & 1)) * U_PITCH] = res[i];
      __syncwarp();
      if (lane == 0) mbar_arrive(bars + 8 * B_PREP);
      TSIF(w == 0, 5);
      mbar_wait(bars + 8 * B_LAST, 0);
      prep_gate(p, sb, b, w, lane);
      __syncwarp();
      if (lane == 0) mbar_arrive(bars + 8 * B_GATE);
      TSIF(w == 0, 72);
      mbar_wait(bars + 8 * B_HB, 0);
      TSIF(w == 0, 2);
      const uint32_t ha = sb + U_BYTES + ((tw >> 3) * 16 + 8 + (tw & 7)) * 16;
      uint4 hv[5];
#pragma unroll
      for (int c = 0; c < 5; c++) hv[c] = lds128(ha + off_ch(c));
      __syncwarp();
#pragma unroll
      for (int c = 0; c < 5; c++) sts128((ha ^ 16) + off_ch(c), hv[c].x, hv[c].y, hv[c].z, hv[c].w);
      asm volatile("st.shared.v2.u32 [%0], {%1, %2};" ::"r"(sb + OFF_TT + 8 * tw), "r"(tt[0]), "r"(tt[1]) : "memory");
      if (tw < 5) asm volatile("st.shared.f32 [%0], %1;" ::"r"(sb + OFF_D + 4 * tw), "f"(bf_lo(dv) * 0.125f) : "memory");
      fence_async_smem();
      __syncwarp();
      if (lane == 0) mbar_arrive(bars + 8 * B_HA);
      TSIF(w == 0, 6);
      mbar_wait(bars + 8 * B_HA, 0);
      fft_matrices(fc, sb, w, lane);
    }

    TSM(w == 0 && wg == 2, 124);
#pragma unroll 1
    for (uint32_t tasks = wg == 0 ? TASK0 : wg == 1 ? TASK1 : TASK2; tasks; tasks >>= 4) {
      const int c = (tasks & 7) - 1;
      conv_channel(fc, sb, c, wg, w, lane);
      if (lane == 0) mbar_arrive(bars + 8 * (B_YST + c));
      TSM(w == 0, 10 + c);
    }

    if (wg != 1) {
      const int wg = warp >> 3;
      const int g = lane >> 2;
      float acc[40];
#pragma unroll
      for (int i = 0; i < 40; i++) acc[i] = 0.f;
      const uint32_t da = desc_lo(sb + wg * 1024, 2048), db = desc_lo(sb, 2560);
      mbar_wait(bars + 8 * B_ORB, 0);
      mbar_wait(bars + 8 * B_FULL2, 0);
      TSM(w == 0, 15 + wg);
#pragma unroll 1
      for (int j = 0; j < 8; j++) {
        if (j == 1 - wg) mbar_wait(bars + 8 * B_CVD, 0);
        mbar_wait(bars + 8 * (B_FULL2 + j), 0);
        TSM(w == 0 && wg == 0, 44 + (j < 4 ? j : j + 6));
        const uint32_t oa = da + (off_o(j) >> 4), ob = db + (off_w(j) >> 4);
        wg_fence();
#pragma unroll
        for (int k = 0; k < 5; k++) WgSST<80>::mma<HI_NONE, HI_SW32>(acc, oa + 256 * k, ob + 32 * k, 1);
        wg_commit();
        wg_wait<1>();
        if (j >= 1 && j <= 4 && lane == 0) mbar_arrive(bars + 8 * (B_EMPTY2 + j - 1));
      }
      TSIF(w == 0 && wg == 0, 113);
      const int tr = 64 * wg + 16 * w + (lane & 15);
      const uint32_t fm = sb + OFF_QS + tr * 128, fx = (lane >> 4) ^ (tr & 7);
      const uint32_t ft = sb + OFF_QT + tr * 32 + (((lane >> 4) ^ (tr >> 2)) & 1) * 16;
      const float g0 = __uint_as_float(lds32(sb + OFF_GATE + (64 * wg + 16 * w + g) * 4));
      const float g1 = __uint_as_float(lds32(sb + OFF_GATE + (64 * wg + 16 * w + 8 + g) * 4));
      const uint32_t ga = pack2(g0, g0), gb = pack2(g1, g1);
      const uint32_t na = pack2(1.f - g0, 1.f - g0), nb = pack2(1.f - g1, 1.f - g1);

      uint32_t qf[20];
      mbar_wait(bars + 8 * B_QF, 0);
      TSM(w == 0 && wg == 0, 99);
#pragma unroll
      for (int j = 0; j < 5; j++) ldsm4(qf + 4 * j, j < 4 ? fm + ((fx ^ (2 * j)) << 4) : ft);
#pragma unroll
      for (int i = 0; i < 20; i++) {
        qf[i] = bmul((i & 1) ? gb : ga, qf[i]);
        asm volatile("" : "+r"(qf[i]));
      }

      wg_wait<0>();
      pin<40>(acc);
      TSM(w == 0, 17 + wg);
      uint32_t pb[20];
#pragma unroll
      for (int j = 0; j < 10; j++) {
        pb[2 * j] = bmul(na, pack2(acc[4 * j], acc[4 * j + 1]));
        pb[2 * j + 1] = bmul(nb, pack2(acc[4 * j + 2], acc[4 * j + 3]));
        asm volatile("" : "+r"(pb[2 * j]), "+r"(pb[2 * j + 1]));
      }
      const uint32_t ya = sb + OFF_YT + wg * 10240 + ((lane >> 4) * 8 + (lane & 7)) * 128 +
                          (((2 * w + (((lane >> 3) & 1) ^ wg)) ^ (lane & 7)) << 4);
      mbar_wait(bars + 8 * B_YFULL, 0);
      TSM(w == 0 && wg == 0, 19);
#pragma unroll
      for (int j = 0; j < 5; j++) {
        uint32_t y[4];
        ldsm4t(y, ya + 2048 * j);
#pragma unroll
        for (int i = 0; i < 4; i++)
          qf[4 * j + i] = bfma(qf[4 * j + i], y[i], pb[4 * j + i]);
      }
#pragma unroll
      for (int j = 0; j < 5; j++) stsm4(j < 4 ? fm + ((fx ^ (2 * j)) << 4) : ft, qf + 4 * j);
      fence_async_smem();
      __syncwarp();
      if (lane == 0) {
        const int row = 64 * wg + 16 * w;
        asm volatile("cp.async.bulk.tensor.2d.global.shared::cta.bulk_group [%0, {%2, %3}], [%1];"
                     ::"l"(&m.om), "r"(sb + OFF_QS + row * 128), "r"(80 * hg), "r"(128 * r + row) : "memory");
        asm volatile("cp.async.bulk.tensor.2d.global.shared::cta.bulk_group [%0, {%2, %3}], [%1];"
                     ::"l"(&m.ot), "r"(sb + OFF_QT + row * 32), "r"(80 * hg + 64), "r"(128 * r + row) : "memory");
        asm volatile("cp.async.bulk.commit_group;\ncp.async.bulk.wait_group.read 0;" ::: "memory");
      }
      TSM(w == 0 || w == 3, 40 + 2 * wg + (w & 1));
    }
  }
}

typedef CUresult (*EncodeFn)(CUtensorMap*, CUtensorMapDataType, cuuint32_t, void*, const cuuint64_t*, const cuuint64_t*,
                             const cuuint32_t*, const cuuint32_t*, CUtensorMapInterleave, CUtensorMapSwizzle,
                             CUtensorMapL2promotion, CUtensorMapFloatOOBfill);

void encode(EncodeFn fn, CUtensorMap* tm, const void* base, int rank, const cuuint64_t* dims, const cuuint64_t* strides,
            const cuuint32_t* box, CUtensorMapSwizzle swz) {
  const cuuint32_t ones[3] = {1, 1, 1};
  fn(tm, CU_TENSOR_MAP_DATA_TYPE_BFLOAT16, rank, const_cast<void*>(base), dims, strides, box, ones,
     CU_TENSOR_MAP_INTERLEAVE_NONE, swz, CU_TENSOR_MAP_L2_PROMOTION_L2_128B, CU_TENSOR_MAP_FLOAT_OOB_FILL_NONE);
}

}

extern "C" void kernel_launch(void* const* d_in, const int* in_sizes, int n_in, void* d_out, int out_size) {
  (void)in_sizes; (void)n_in; (void)out_size;
  Params p;
  p.q = (const __nv_bfloat16*)d_in[0];
  p.k = (const __nv_bfloat16*)d_in[1];
  p.v = (const __nv_bfloat16*)d_in[2];
  p.shift_k = (const __nv_bfloat16*)d_in[3];
  p.ssm_k = (const __nv_bfloat16*)d_in[4];
  p.ssm_D = (const __nv_bfloat16*)d_in[5];
  p.wqkv = (const __nv_bfloat16*)d_in[7];
  p.wo = (const __nv_bfloat16*)d_in[8];
  p.gate_w = (const __nv_bfloat16*)d_in[9];
  p.out = (__nv_bfloat16*)d_out;
  p.zero = 0;

  static EncodeFn fn = nullptr;
  static void *yaddr = nullptr, *oaddr = nullptr;
  if (!fn) {
    cudaDriverEntryPointQueryResult qr;
    void* f = nullptr;
    cudaGetDriverEntryPoint("cuTensorMapEncodeTiled", &f, cudaEnableDefault, &qr);
    fn = (EncodeFn)f;
    cudaGetSymbolAddress(&yaddr, g_U);
    cudaGetSymbolAddress(&oaddr, g_O);
    cudaFuncSetAttribute(fused_kernel, cudaFuncAttributeMaxDynamicSharedMemorySize, SMEM_BYTES);
  }
  Maps m;
  {
    const cuuint64_t dims[3] = {640, 1024, 2}, st[2] = {2560, 1280};
    const cuuint32_t box[3] = {64, 64, 2};
    encode(fn, &m.x, p.q, 3, dims, st, box, CU_TENSOR_MAP_SWIZZLE_128B);
  }
  {
    const cuuint64_t dims[3] = {640, 640, 3}, st[2] = {3840, 1280};
    const cuuint32_t box[3] = {64, 64, 3}, boxt[3] = {16, 64, 3};
    encode(fn, &m.wm, p.wqkv, 3, dims, st, box, CU_TENSOR_MAP_SWIZZLE_128B);
    encode(fn, &m.wt, p.wqkv, 3, dims, st, boxt, CU_TENSOR_MAP_SWIZZLE_32B);
    const cuuint32_t boxh[3] = {64, 16, 3};
    encode(fn, &m.wh, p.wqkv, 3, dims, st, boxh, CU_TENSOR_MAP_SWIZZLE_128B);
  }
  {
    const cuuint64_t dims[3] = {64, 2048, 10}, st[2] = {1280, 128};
    const cuuint32_t boxk[3] = {64, 35, 1}, boxv[3] = {64, 32, 1};
    encode(fn, &m.k, p.k, 3, dims, st, boxk, CU_TENSOR_MAP_SWIZZLE_128B);
    encode(fn, &m.v, p.v, 3, dims, st, boxv, CU_TENSOR_MAP_SWIZZLE_128B);
  }
  {
    const cuuint64_t dims[3] = {16, 640, 40}, st[2] = {1280, 32};
    const cuuint32_t box[3] = {16, 40, 5};
    encode(fn, &m.wo, p.wo, 3, dims, st, box, CU_TENSOR_MAP_SWIZZLE_32B);
  }
  {
    const cuuint64_t dims[2] = {2048, 640}, st[1] = {U_PITCH * 16};
    const cuuint32_t box[2] = {64, 80};
    encode(fn, &m.y, yaddr, 2, dims, st, box, CU_TENSOR_MAP_SWIZZLE_128B);
    const cuuint64_t dl[2] = {64, DIM * U_PITCH / 8}, dol[2] = {64, NCTA * 160}, sl[1] = {128};
    const cuuint32_t bl[2] = {16, 32}, bol[2] = {16, 160};
    encode(fn, &m.yl, yaddr, 2, dl, sl, bl, CU_TENSOR_MAP_SWIZZLE_NONE);
    encode(fn, &m.ol, oaddr, 2, dol, sl, bol, CU_TENSOR_MAP_SWIZZLE_NONE);
  }
  {
    const cuuint64_t dims[2] = {640, 2048}, st[1] = {1280};
    const cuuint32_t bqm[2] = {64, 128}, bqt[2] = {16, 128}, bom[2] = {64, 16}, bot[2] = {16, 16};
    encode(fn, &m.qm, p.q, 2, dims, st, bqm, CU_TENSOR_MAP_SWIZZLE_128B);
    encode(fn, &m.qt, p.q, 2, dims, st, bqt, CU_TENSOR_MAP_SWIZZLE_32B);
    encode(fn, &m.om, p.out, 2, dims, st, bom, CU_TENSOR_MAP_SWIZZLE_128B);
    encode(fn, &m.ot, p.out, 2, dims, st, bot, CU_TENSOR_MAP_SWIZZLE_32B);
  }
  fused_kernel<<<NCTA, NTHR, SMEM_BYTES>>>(m, p);
}
```
